```python
import torch

def _softmax(x, axis=-1):
    return torch.softmax(x, dim=axis)
def _gelu(x):
    return torch.nn.functional.gelu(x, approximate="tanh")
def _silu(x):
    return torch.nn.functional.silu(x)
def _sigmoid(x):
    return torch.sigmoid(x)
def _layernorm(x, axis=-1, eps=1e-5):
    m = x.mean(dim=axis, keepdim=True)
    v = x.var(dim=axis, keepdim=True, unbiased=False)
    return (x - m) / torch.sqrt(v + eps)
def _scatter_add(tgt, idx, src, axis=0):
    return tgt.clone().index_add_(axis, idx, src)
def _segment_sum(src, seg, n):
    out = torch.zeros((n,) + src.shape[1:], dtype=src.dtype)
    return out.index_add_(0, seg, src)
def _pad(x, pw):
    flat = tuple(v for pair in reversed(pw) for v in pair)
    return torch.nn.functional.pad(x, flat)

kernel_name = 'concat_heads__ssm_conv_h3__linear_attn_block__prompt'

def setup_inputs():

    _w = (lambda a: (lambda t: t.to(torch.bfloat16) if t.is_floating_point() else t)(torch.as_tensor(a)))
    def _A_setup():
        B, S, D = 1, 2048, 1024
        ks = 4
        return {
            "q": _w((lambda *s: torch.randn(*s, dtype=torch.bfloat16) * 0.05)(B, S, D)),
            "k": _w((lambda *s: torch.randn(*s, dtype=torch.bfloat16) * 0.4)(B, S, D)),
            "v": _w((lambda *s: torch.randn(*s, dtype=torch.bfloat16) * 0.4)(B, S, D)),
            "shift_k": _w((lambda *s: torch.randn(*s, dtype=torch.bfloat16) * 0.4)(D, ks) * 0.5),
            "ssm_k": _w((lambda *s: torch.randn(*s, dtype=torch.bfloat16) * 1.6)(D, S) * (1.0 / S ** 0.5)),
            "ssm_D": _w((lambda *s: torch.randn(*s, dtype=torch.bfloat16) * 0.4)(D)),
        }
    _A_in = _A_setup()

    def _B_setup():
        B, S, D = 1, 2048, 1024
        return {
            "x": _w((lambda *s: torch.randn(*s, dtype=torch.bfloat16) * 0.05)(B, S, D)),
            "wqkv": _w((lambda *s: torch.randn(*s, dtype=torch.bfloat16) * 0.8)(D, 3 * D)),
            "wo": _w((lambda *s: torch.randn(*s, dtype=torch.bfloat16) * 0.05)(D, D)),
        }
    _B_in = _B_setup()

    return {
        "A_q": _A_in["q"],
        "A_k": _A_in["k"],
        "A_v": _A_in["v"],
        "A_shift_k": _A_in["shift_k"],
        "A_ssm_k": _A_in["ssm_k"],
        "A_ssm_D": _A_in["ssm_D"],
        "B_x": _B_in["x"],
        "B_wqkv": _B_in["wqkv"],
        "B_wo": _B_in["wo"],
    }

def reference(A_q, A_k, A_v, A_shift_k, A_ssm_k, A_ssm_D, B_x, B_wqkv, B_wo):
    def _A_ref(q, k, v, shift_k, ssm_k, ssm_D):
        B, S, D = q.shape
        ks = shift_k.shape[-1]
        k_pad = _pad(k, ((0, 0), (ks - 1, 0), (0, 0)))
        k_shift = torch.zeros_like(k)
        for t in range(ks):
            k_shift = k_shift + k_pad[:, t:t + S, :] * shift_k[:, ks - 1 - t][None, None, :]
        kv = k_shift * v
        L = 2 * S
        kv_pad = _pad(kv, ((0, 0), (0, S), (0, 0)))
        kf_pad = _pad(ssm_k, ((0, 0), (0, S)))
        kv_f = (lambda x, axes=(-2,-1): torch.fft.rfft2(x.float(), dim=axes))(kv_pad[:, None, :, :], axes=(1, 2))
        kf_f = (lambda x, axes=(-2,-1): torch.fft.rfft2(x.float(), dim=axes))(kf_pad[:, None, :], axes=(1, 2))
        kf_f = (lambda x, *d: x.permute(*d))(kf_f, 1, 2, 0)
        y_f = kv_f * kf_f[None, :, :, :]
        y = (lambda x, s, axes=(-2,-1): torch.fft.irfft2(x, s=s, dim=axes).to(torch.bfloat16))(y_f, (1, L), axes=(1, 2))[:, 0, :S, :]
        y = y + kv * ssm_D[None, None, :]
        return q * y

    def _B_ref(x, wqkv, wo):
        B, S, D = x.shape
        H = 32; Dh = D // H
        qkv = (lambda x, *d: x.permute(*d))((x @ wqkv).reshape(B, S, 3, H, Dh), 2, 0, 3, 1, 4)
        q, k, v = qkv[0], qkv[1], qkv[2]
        phi = lambda t: torch.where(t > 0, t + 1, torch.exp(t)) + 1e-6
        pq, pk = phi(q), phi(k)
        kv = torch.einsum("bhsd,bhse->bhde", pk, v)
        z = torch.einsum("bhsd->bhd", pk)
        num = torch.einsum("bhqd,bhde->bhqe", pq, kv)
        den = torch.einsum("bhqd,bhd->bhq", pq, z)[..., None] + 1e-6
        o = num / den
        return (lambda x, *d: x.permute(*d))(o, 0, 2, 1, 3).reshape(B, S, D) @ wo

    a = _A_ref(A_q, A_k, A_v, A_shift_k, A_ssm_k, A_ssm_D)
    b = _B_ref(B_x, B_wqkv, B_wo)
    return torch.concatenate([a, b], axis=-1)
```

```cpp
#include <cuda_runtime.h>
#include <cuda_bf16.h>
#include <cuda.h>
#include <stdint.h>

template<int TA, int TB, int SA=1> __device__ __forceinline__ void wgmma_ss_n192(float (&d)[96], uint64_t da, uint64_t db, int scale_d) {
  asm volatile("{\n.reg .pred p;\nsetp.ne.b32 p, %98, 0;\n"
    "wgmma.mma_async.sync.aligned.m64n192k16.f32.bf16.bf16 {%0, %1, %2, %3, %4, %5, %6, %7, %8, %9, %10, %11, %12, %13, %14, %15, %16, %17, %18, %19, %20, %21, %22, %23, %24, %25, %26, %27, %28, %29, %30, %31, %32, %33, %34, %35, %36, %37, %38, %39, %40, %41, %42, %43, %44, %45, %46, %47, %48, %49, %50, %51, %52, %53, %54, %55, %56, %57, %58, %59, %60, %61, %62, %63, %64, %65, %66, %67, %68, %69, %70, %71, %72, %73, %74, %75, %76, %77, %78, %79, %80, %81, %82, %83, %84, %85, %86, %87, %88, %89, %90, %91, %92, %93, %94, %95}, %96, %97, p, %101, 1, %99, %100;\n}\n"
    : "+f"(d[0]), "+f"(d[1]), "+f"(d[2]), "+f"(d[3]), "+f"(d[4]), "+f"(d[5]), "+f"(d[6]), "+f"(d[7]), "+f"(d[8]), "+f"(d[9]), "+f"(d[10]), "+f"(d[11]), "+f"(d[12]), "+f"(d[13]), "+f"(d[14]), "+f"(d[15]), "+f"(d[16]), "+f"(d[17]), "+f"(d[18]), "+f"(d[19]), "+f"(d[20]), "+f"(d[21]), "+f"(d[22]), "+f"(d[23]), "+f"(d[24]), "+f"(d[25]), "+f"(d[26]), "+f"(d[27]), "+f"(d[28]), "+f"(d[29]), "+f"(d[30]), "+f"(d[31]), "+f"(d[32]), "+f"(d[33]), "+f"(d[34]), "+f"(d[35]), "+f"(d[36]), "+f"(d[37]), "+f"(d[38]), "+f"(d[39]), "+f"(d[40]), "+f"(d[41]), "+f"(d[42]), "+f"(d[43]), "+f"(d[44]), "+f"(d[45]), "+f"(d[46]), "+f"(d[47]), "+f"(d[48]), "+f"(d[49]), "+f"(d[50]), "+f"(d[51]), "+f"(d[52]), "+f"(d[53]), "+f"(d[54]), "+f"(d[55]), "+f"(d[56]), "+f"(d[57]), "+f"(d[58]), "+f"(d[59]), "+f"(d[60]), "+f"(d[61]), "+f"(d[62]), "+f"(d[63]), "+f"(d[64]), "+f"(d[65]), "+f"(d[66]), "+f"(d[67]), "+f"(d[68]), "+f"(d[69]), "+f"(d[70]), "+f"(d[71]), "+f"(d[72]), "+f"(d[73]), "+f"(d[74]), "+f"(d[75]), "+f"(d[76]), "+f"(d[77]), "+f"(d[78]), "+f"(d[79]), "+f"(d[80]), "+f"(d[81]), "+f"(d[82]), "+f"(d[83]), "+f"(d[84]), "+f"(d[85]), "+f"(d[86]), "+f"(d[87]), "+f"(d[88]), "+f"(d[89]), "+f"(d[90]), "+f"(d[91]), "+f"(d[92]), "+f"(d[93]), "+f"(d[94]), "+f"(d[95])
    : "l"(da), "l"(db), "r"(scale_d), "n"(TA), "n"(TB), "n"(SA));
}
template<int TA, int TB, int SA=1> __device__ __forceinline__ void wgmma_ss_n128(float (&d)[64], uint64_t da, uint64_t db, int scale_d) {
  asm volatile("{\n.reg .pred p;\nsetp.ne.b32 p, %66, 0;\n"
    "wgmma.mma_async.sync.aligned.m64n128k16.f32.bf16.bf16 {%0, %1, %2, %3, %4, %5, %6, %7, %8, %9, %10, %11, %12, %13, %14, %15, %16, %17, %18, %19, %20, %21, %22, %23, %24, %25, %26, %27, %28, %29, %30, %31, %32, %33, %34, %35, %36, %37, %38, %39, %40, %41, %42, %43, %44, %45, %46, %47, %48, %49, %50, %51, %52, %53, %54, %55, %56, %57, %58, %59, %60, %61, %62, %63}, %64, %65, p, %69, 1, %67, %68;\n}\n"
    : "+f"(d[0]), "+f"(d[1]), "+f"(d[2]), "+f"(d[3]), "+f"(d[4]), "+f"(d[5]), "+f"(d[6]), "+f"(d[7]), "+f"(d[8]), "+f"(d[9]), "+f"(d[10]), "+f"(d[11]), "+f"(d[12]), "+f"(d[13]), "+f"(d[14]), "+f"(d[15]), "+f"(d[16]), "+f"(d[17]), "+f"(d[18]), "+f"(d[19]), "+f"(d[20]), "+f"(d[21]), "+f"(d[22]), "+f"(d[23]), "+f"(d[24]), "+f"(d[25]), "+f"(d[26]), "+f"(d[27]), "+f"(d[28]), "+f"(d[29]), "+f"(d[30]), "+f"(d[31]), "+f"(d[32]), "+f"(d[33]), "+f"(d[34]), "+f"(d[35]), "+f"(d[36]), "+f"(d[37]), "+f"(d[38]), "+f"(d[39]), "+f"(d[40]), "+f"(d[41]), "+f"(d[42]), "+f"(d[43]), "+f"(d[44]), "+f"(d[45]), "+f"(d[46]), "+f"(d[47]), "+f"(d[48]), "+f"(d[49]), "+f"(d[50]), "+f"(d[51]), "+f"(d[52]), "+f"(d[53]), "+f"(d[54]), "+f"(d[55]), "+f"(d[56]), "+f"(d[57]), "+f"(d[58]), "+f"(d[59]), "+f"(d[60]), "+f"(d[61]), "+f"(d[62]), "+f"(d[63])
    : "l"(da), "l"(db), "r"(scale_d), "n"(TA), "n"(TB), "n"(SA));
}
template<int TA, int TB, int SA=1> __device__ __forceinline__ void wgmma_ss_n72(float (&d)[36], uint64_t da, uint64_t db, int scale_d) {
  asm volatile("{\n.reg .pred p;\nsetp.ne.b32 p, %38, 0;\n"
    "wgmma.mma_async.sync.aligned.m64n72k16.f32.bf16.bf16 {%0, %1, %2, %3, %4, %5, %6, %7, %8, %9, %10, %11, %12, %13, %14, %15, %16, %17, %18, %19, %20, %21, %22, %23, %24, %25, %26, %27, %28, %29, %30, %31, %32, %33, %34, %35}, %36, %37, p, %41, 1, %39, %40;\n}\n"
    : "+f"(d[0]), "+f"(d[1]), "+f"(d[2]), "+f"(d[3]), "+f"(d[4]), "+f"(d[5]), "+f"(d[6]), "+f"(d[7]), "+f"(d[8]), "+f"(d[9]), "+f"(d[10]), "+f"(d[11]), "+f"(d[12]), "+f"(d[13]), "+f"(d[14]), "+f"(d[15]), "+f"(d[16]), "+f"(d[17]), "+f"(d[18]), "+f"(d[19]), "+f"(d[20]), "+f"(d[21]), "+f"(d[22]), "+f"(d[23]), "+f"(d[24]), "+f"(d[25]), "+f"(d[26]), "+f"(d[27]), "+f"(d[28]), "+f"(d[29]), "+f"(d[30]), "+f"(d[31]), "+f"(d[32]), "+f"(d[33]), "+f"(d[34]), "+f"(d[35])
    : "l"(da), "l"(db), "r"(scale_d), "n"(TA), "n"(TB), "n"(SA));
}
template<int TB, int SA=1> __device__ __forceinline__ void wgmma_rs_n64(float (&d)[32], uint32_t a0, uint32_t a1, uint32_t a2, uint32_t a3, uint64_t db, int scale_d) {
  asm volatile("{\n.reg .pred p;\nsetp.ne.b32 p, %37, 0;\n"
    "wgmma.mma_async.sync.aligned.m64n64k16.f32.bf16.bf16 {%0, %1, %2, %3, %4, %5, %6, %7, %8, %9, %10, %11, %12, %13, %14, %15, %16, %17, %18, %19, %20, %21, %22, %23, %24, %25, %26, %27, %28, %29, %30, %31}, {%32, %33, %34, %35}, %36, p, %39, 1, %38;\n}\n"
    : "+f"(d[0]), "+f"(d[1]), "+f"(d[2]), "+f"(d[3]), "+f"(d[4]), "+f"(d[5]), "+f"(d[6]), "+f"(d[7]), "+f"(d[8]), "+f"(d[9]), "+f"(d[10]), "+f"(d[11]), "+f"(d[12]), "+f"(d[13]), "+f"(d[14]), "+f"(d[15]), "+f"(d[16]), "+f"(d[17]), "+f"(d[18]), "+f"(d[19]), "+f"(d[20]), "+f"(d[21]), "+f"(d[22]), "+f"(d[23]), "+f"(d[24]), "+f"(d[25]), "+f"(d[26]), "+f"(d[27]), "+f"(d[28]), "+f"(d[29]), "+f"(d[30]), "+f"(d[31])
    : "r"(a0), "r"(a1), "r"(a2), "r"(a3), "l"(db), "r"(scale_d), "n"(TB), "n"(SA));
}
template<int TB, int SA=1> __device__ __forceinline__ void wgmma_rs_n40(float (&d)[20], uint32_t a0, uint32_t a1, uint32_t a2, uint32_t a3, uint64_t db, int scale_d) {
  asm volatile("{\n.reg .pred p;\nsetp.ne.b32 p, %25, 0;\n"
    "wgmma.mma_async.sync.aligned.m64n40k16.f32.bf16.bf16 {%0, %1, %2, %3, %4, %5, %6, %7, %8, %9, %10, %11, %12, %13, %14, %15, %16, %17, %18, %19}, {%20, %21, %22, %23}, %24, p, %27, 1, %26;\n}\n"
    : "+f"(d[0]), "+f"(d[1]), "+f"(d[2]), "+f"(d[3]), "+f"(d[4]), "+f"(d[5]), "+f"(d[6]), "+f"(d[7]), "+f"(d[8]), "+f"(d[9]), "+f"(d[10]), "+f"(d[11]), "+f"(d[12]), "+f"(d[13]), "+f"(d[14]), "+f"(d[15]), "+f"(d[16]), "+f"(d[17]), "+f"(d[18]), "+f"(d[19])
    : "r"(a0), "r"(a1), "r"(a2), "r"(a3), "l"(db), "r"(scale_d), "n"(TB), "n"(SA));
}
template<int TB, int SA=1> __device__ __forceinline__ void wgmma_rs_n32(float (&d)[16], uint32_t a0, uint32_t a1, uint32_t a2, uint32_t a3, uint64_t db, int scale_d) {
  asm volatile("{\n.reg .pred p;\nsetp.ne.b32 p, %21, 0;\n"
    "wgmma.mma_async.sync.aligned.m64n32k16.f32.bf16.bf16 {%0, %1, %2, %3, %4, %5, %6, %7, %8, %9, %10, %11, %12, %13, %14, %15}, {%16, %17, %18, %19}, %20, p, %23, 1, %22;\n}\n"
    : "+f"(d[0]), "+f"(d[1]), "+f"(d[2]), "+f"(d[3]), "+f"(d[4]), "+f"(d[5]), "+f"(d[6]), "+f"(d[7]), "+f"(d[8]), "+f"(d[9]), "+f"(d[10]), "+f"(d[11]), "+f"(d[12]), "+f"(d[13]), "+f"(d[14]), "+f"(d[15])
    : "r"(a0), "r"(a1), "r"(a2), "r"(a3), "l"(db), "r"(scale_d), "n"(TB), "n"(SA));
}

__device__ __align__(128) const uint32_t c_thr[4096] = {
  0x3f803f80,0xbd498000,0x3f673f6d,0xbedbbec4,0x3f7d3f7f,0xbe16bdc9,0x3f5c3f62,0xbf04bef1,0x3f783f7b,0xbe79be48,0x3f4e3f55,0xbf18bf0e,
  0x3f713f75,0xbeacbe95,0x3f3e3f46,0xbf2cbf22,0x3f7d3f80,0xbe168000,0x3e793ec4,0xbf78bf6d,0x3f673f75,0xbedbbe95,0xbd493dc9,0xbf80bf7f,
  0x3f3e3f55,0xbf2cbf0e,0xbeacbe48,0xbf71bf7b,0x3f043f22,0xbf5cbf46,0xbf18bef1,0xbf4ebf62,0x3f783f80,0xbe798000,0xbf18bec4,0xbf4ebf6d,
  0x3f3e3f62,0xbf2cbef1,0xbf67bf46,0xbedbbf22,0x3eac3f0e,0xbf71bf55,0xbf80bf7b,0x3d49be48,0xbe163dc9,0xbf7dbf7f,0xbf5cbf75,0x3f043e95,
  0x3f713f80,0xbeac8000,0xbf80bf6d,0xbd49bec4,0x3f043f46,0xbf5cbf22,0xbf4ebf75,0x3f183e95,0xbe163e48,0xbf7dbf7b,0xbe79bf0e,0x3f783f55,
  0xbf3ebef1,0xbf2cbf62,0x3edb3dc9,0x3f673f7f,0x3f673f80,0xbedb8000,0xbf2cbf6d,0x3f3e3ec4,0x3e793f22,0xbf78bf46,0x3e16be95,0x3f7d3f75,
  0xbf18be48,0xbf4ebf7b,0x3f5c3f0e,0x3f043f55,0xbf80bf62,0xbd49bef1,0x3f713f7f,0xbeac3dc9,0x3f5c3f80,0xbf048000,0x3e16bec4,0x3f7d3f6d,
  0xbd493ef1,0xbf80bf62,0x3f713f22,0x3eac3f46,0xbf67bf0e,0xbedbbf55,0x3f3e3f7b,0xbf2cbe48,0xbf4ebf7f,0x3f183dc9,0xbe793e95,0xbf78bf75,
  0x3f4e3f80,0xbf188000,0x3f5c3ec4,0x3f043f6d,0xbeac3e95,0xbf71bf75,0x3f3e3f7f,0xbf2cbdc9,0xbf80bf55,0x3d49bf0e,0xbedb3e48,0xbf67bf7b,
  0xbe79bf46,0x3f783f22,0xbf7dbf62,0x3e16bef1,0x3f3e3f80,0xbf2c8000,0x3f713f6d,0xbeac3ec4,0xbf183dc9,0xbf4ebf7f,0xbe793ef1,0xbf78bf62,
  0xbf5cbf7b,0x3f04be48,0xbf7dbf55,0x3e16bf0e,0x3edbbe95,0x3f673f75,0x3d49bf22,0x3f803f46,0x3f2c3f80,0xbf3e8000,0x3eac3f6d,0xbf71bec4,
  0xbf4ebdc9,0xbf18bf7f,0xbf78bef1,0xbe79bf62,0xbf04bf7b,0x3f5c3e48,0xbe16bf55,0x3f7d3f0e,0x3f673e95,0x3edb3f75,0x3f803f22,0x3d493f46,
  0x3f183f80,0xbf4e8000,0xbf043ec4,0xbf5cbf6d,0xbf71be95,0xbeacbf75,0xbf2cbf7f,0x3f3ebdc9,0xbd49bf55,0x3f803f0e,0x3f673e48,0x3edb3f7b,
  0x3f783f46,0xbe793f22,0x3e163f62,0xbf7dbef1,0x3f043f80,0xbf5c8000,0xbf7dbec4,0xbe16bf6d,0xbf80bef1,0xbd49bf62,0x3eacbf22,0x3f713f46,
  0x3edbbf0e,0x3f673f55,0x3f2c3f7b,0xbf3e3e48,0x3f183f7f,0xbf4e3dc9,0xbf78be95,0xbe79bf75,0x3edb3f80,0xbf678000,0xbf3ebf6d,0x3f2cbec4,
  0xbf78bf22,0x3e79bf46,0x3f7d3e95,0x3e163f75,0x3f4ebe48,0x3f183f7b,0xbf043f0e,0xbf5cbf55,0xbd493f62,0xbf80bef1,0xbeacbf7f,0x3f713dc9,
  0x3eac3f80,0xbf718000,0x3d49bf6d,0x3f803ec4,0xbf5cbf46,0x3f04bf22,0x3f183f75,0xbf4e3e95,0x3f7d3e48,0x3e163f7b,0xbf78bf0e,0x3e79bf55,
  0xbf2c3ef1,0xbf3ebf62,0x3f67bdc9,0x3edb3f7f,0x3e793f80,0xbf788000,0x3f4ebec4,0x3f183f6d,0xbf2cbf62,0x3f3ebef1,0xbedb3f46,0xbf67bf22,
  0x3f713f0e,0xbeac3f55,0xbd49bf7b,0x3f803e48,0xbf7dbdc9,0xbe16bf7f,0x3f043f75,0xbf5c3e95,0x3e163f80,0xbf7d8000,0x3f783ec4,0xbe793f6d,
  0xbedbbf75,0x3f67be95,0xbf80bdc9,0xbd49bf7f,0x3f2c3f55,0xbf3e3f0e,0x3f71be48,0x3eac3f7b,0xbf5cbf22,0x3f04bf46,0xbf4e3ef1,0xbf18bf62,
  0x3d493f80,0xbf808000,0x3edb3f6d,0xbf673ec4,0xbe16bf7f,0x3f7dbdc9,0xbf04bf62,0x3f5cbef1,0x3e793f7b,0xbf783e48,0x3f183f55,0xbf4e3f0e,
  0xbeacbf75,0x3f71be95,0xbf2cbf46,0x3f3ebf22,0xbd493f80,0xbf808000,0xbedb3f6d,0xbf67bec4,0x3e16bf7f,0x3f7d3dc9,0x3f04bf62,0x3f5c3ef1,
  0xbe793f7b,0xbf78be48,0xbf183f55,0xbf4ebf0e,0x3eacbf75,0x3f713e95,0x3f2cbf46,0x3f3e3f22,0xbe163f80,0xbf7d8000,0xbf783ec4,0xbe79bf6d,
  0x3edbbf75,0x3f673e95,0x3f80bdc9,0xbd493f7f,0xbf2c3f55,0xbf3ebf0e,0xbf71be48,0x3eacbf7b,0x3f5cbf22,0x3f043f46,0x3f4e3ef1,0xbf183f62,
  0xbe793f80,0xbf788000,0xbf4ebec4,0x3f18bf6d,0x3f2cbf62,0x3f3e3ef1,0x3edb3f46,0xbf673f22,0xbf713f0e,0xbeacbf55,0x3d49bf7b,0x3f80be48,
  0x3f7dbdc9,0xbe163f7f,0xbf043f75,0xbf5cbe95,0xbeac3f80,0xbf718000,0xbd49bf6d,0x3f80bec4,0x3f5cbf46,0x3f043f22,0xbf183f75,0xbf4ebe95,
  0xbf7d3e48,0x3e16bf7b,0x3f78bf0e,0x3e793f55,0x3f2c3ef1,0xbf3e3f62,0xbf67bdc9,0x3edbbf7f,0xbedb3f80,0xbf678000,0x3f3ebf6d,0x3f2c3ec4,
  0x3f78bf22,0x3e793f46,0xbf7d3e95,0x3e16bf75,0xbf4ebe48,0x3f18bf7b,0x3f043f0e,0xbf5c3f55,0x3d493f62,0xbf803ef1,0x3eacbf7f,0x3f71bdc9,
  0xbf043f80,0xbf5c8000,0x3f7dbec4,0xbe163f6d,0x3f80bef1,0xbd493f62,0xbeacbf22,0x3f71bf46,0xbedbbf0e,0x3f67bf55,0xbf2c3f7b,0xbf3ebe48,
  0xbf183f7f,0xbf4ebdc9,0x3f78be95,0xbe793f75,0xbf183f80,0xbf4e8000,0x3f043ec4,0xbf5c3f6d,0x3f71be95,0xbeac3f75,0x3f2cbf7f,0x3f3e3dc9,
  0x3d49bf55,0x3f80bf0e,0xbf673e48,0x3edbbf7b,0xbf783f46,0xbe79bf22,0xbe163f62,0xbf7d3ef1,0xbf2c3f80,0xbf3e8000,0xbeac3f6d,0xbf713ec4,
  0x3f4ebdc9,0xbf183f7f,0x3f78bef1,0xbe793f62,0x3f04bf7b,0x3f5cbe48,0x3e16bf55,0x3f7dbf0e,0xbf673e95,0x3edbbf75,0xbf803f22,0x3d49bf46,
  0xbf3e3f80,0xbf2c8000,0xbf713f6d,0xbeacbec4,0x3f183dc9,0xbf4e3f7f,0x3e793ef1,0xbf783f62,0x3f5cbf7b,0x3f043e48,0x3f7dbf55,0x3e163f0e,
  0xbedbbe95,0x3f67bf75,0xbd49bf22,0x3f80bf46,0xbf4e3f80,0xbf188000,0xbf5c3ec4,0x3f04bf6d,0x3eac3e95,0xbf713f75,0xbf3e3f7f,0xbf2c3dc9,
  0x3f80bf55,0x3d493f0e,0x3edb3e48,0xbf673f7b,0x3e79bf46,0x3f78bf22,0x3f7dbf62,0x3e163ef1,0xbf5c3f80,0xbf048000,0xbe16bec4,0x3f7dbf6d,
  0x3d493ef1,0xbf803f62,0xbf713f22,0x3eacbf46,0x3f67bf0e,0xbedb3f55,0xbf3e3f7b,0xbf2c3e48,0x3f4ebf7f,0x3f18bdc9,0x3e793e95,0xbf783f75,
  0xbf673f80,0xbedb8000,0x3f2cbf6d,0x3f3ebec4,0xbe793f22,0xbf783f46,0xbe16be95,0x3f7dbf75,0x3f18be48,0xbf4e3f7b,0xbf5c3f0e,0x3f04bf55,
  0x3f80bf62,0xbd493ef1,0xbf713f7f,0xbeacbdc9,0xbf713f80,0xbeac8000,0x3f80bf6d,0xbd493ec4,0xbf043f46,0xbf5c3f22,0x3f4ebf75,0x3f18be95,
  0x3e163e48,0xbf7d3f7b,0x3e79bf0e,0x3f78bf55,0x3f3ebef1,0xbf2c3f62,0xbedb3dc9,0x3f67bf7f,0xbf783f80,0xbe798000,0x3f18bec4,0xbf4e3f6d,
  0xbf3e3f62,0xbf2c3ef1,0x3f67bf46,0xbedb3f22,0xbeac3f0e,0xbf713f55,0x3f80bf7b,0x3d493e48,0x3e163dc9,0xbf7d3f7f,0x3f5cbf75,0x3f04be95,
  0xbf7d3f80,0xbe168000,0xbe793ec4,0xbf783f6d,0xbf673f75,0xbedb3e95,0x3d493dc9,0xbf803f7f,0xbf3e3f55,0xbf2c3f0e,0x3eacbe48,0xbf713f7b,
  0xbf043f22,0xbf5c3f46,0x3f18bef1,0xbf4e3f62,0xbf803f80,0xbd498000,0xbf673f6d,0xbedb3ec4,0xbf7d3f7f,0xbe163dc9,0xbf5c3f62,0xbf043ef1,
  0xbf783f7b,0xbe793e48,0xbf4e3f55,0xbf183f0e,0xbf713f75,0xbeac3e95,0xbf3e3f46,0xbf2c3f22,0x3f2c3f35,0xbf3ebf35,0x3eac3ec4,0xbf71bf6d,
  0x3f183f22,0xbf4ebf46,0x3e793e95,0xbf78bf75,0x3f043f0e,0xbf5cbf55,0x3e163e48,0xbf7dbf7b,0x3edb3ef1,0xbf67bf62,0x3d493dc9,0xbf80bf7f,
  0xbf4ebf35,0xbf18bf35,0xbf5cbf6d,0x3f043ec4,0xbf71bf62,0xbeacbef1,0xbf2cbf46,0x3f3e3f22,0xbf80bf7b,0xbd49be48,0xbedbbf0e,0x3f673f55,
  0xbf78bf7f,0x3e793dc9,0xbe16be95,0x3f7d3f75,0xbf04bf35,0x3f5c3f35,0x3f7d3f6d,0x3e163ec4,0xbd49be95,0x3f803f75,0x3f713f7f,0xbeacbdc9,
  0x3edb3e48,0x3f673f7b,0x3f2c3f55,0xbf3ebf0e,0x3f4e3f22,0x3f183f46,0x3e793ef1,0xbf78bf62,0x3f673f35,0x3edb3f35,0xbf2cbec4,0xbf3ebf6d,
  0x3f783f7f,0xbe793dc9,0xbf7dbf62,0xbe16bef1,0x3f183f55,0xbf4ebf0e,0xbf5cbf7b,0x3f043e48,0xbd493e95,0xbf80bf75,0xbeacbf22,0x3f713f46,
  0x3eac3f35,0xbf71bf35,0x3d49bec4,0x3f803f6d,0xbf04bdc9,0xbf5cbf7f,0x3f4e3ef1,0x3f183f62,0xbf7dbf55,0xbe16bf0e,0x3f783f7b,0xbe793e48,
  0xbf3ebf75,0x3f2c3e95,0x3edb3f46,0xbf67bf22,0xbf78bf35,0xbe79bf35,0x3f183f6d,0xbf4ebec4,0xbf2cbf75,0x3f3e3e95,0xbedb3dc9,0xbf67bf7f,
  0x3eacbe48,0x3f713f7b,0xbf80bf55,0xbd49bf0e,0x3f7d3f46,0x3e163f22,0xbf04bf62,0x3f5c3ef1,0xbe16bf35,0x3f7d3f35,0xbf78bf6d,0x3e79bec4,
  0x3f673ef1,0x3edb3f62,0xbd49bf22,0x3f803f46,0x3f2c3f7b,0xbf3ebe48,0x3f713f0e,0x3eac3f55,0xbf043dc9,0xbf5cbf7f,0x3f183f75,0xbf4ebe95,
  0x3f803f35,0x3d493f35,0x3f673ec4,0x3edb3f6d,0x3e163f46,0xbf7dbf22,0x3f043f75,0xbf5cbe95,0xbf78bf0e,0xbe79bf55,0xbf4ebe48,0xbf18bf7b,
  0xbeacbf62,0x3f713ef1,0xbf2cbf7f,0x3f3e3dc9,0xbd493f35,0xbf80bf35,0xbedb3ec4,0xbf67bf6d,0xbf7dbf46,0x3e16bf22,0xbf5cbf75,0x3f04be95,
  0x3e79bf0e,0x3f783f55,0x3f18be48,0x3f4e3f7b,0x3f713f62,0xbeac3ef1,0x3f3e3f7f,0xbf2c3dc9,0xbf7dbf35,0x3e16bf35,0xbe79bf6d,0x3f783ec4,
  0x3edbbef1,0x3f673f62,0x3f803f22,0xbd493f46,0x3f3e3f7b,0xbf2c3e48,0xbeac3f0e,0xbf71bf55,0xbf5cbdc9,0xbf04bf7f,0xbf4ebf75,0x3f18be95,
  0x3e79bf35,0x3f783f35,0x3f4e3f6d,0xbf183ec4,0x3f3e3f75,0xbf2c3e95,0xbf67bdc9,0xbedbbf7f,0xbf71be48,0xbeacbf7b,0x3d49bf55,0x3f803f0e,
  0x3e16bf46,0x3f7d3f22,0x3f5c3f62,0xbf043ef1,0x3f713f35,0xbeac3f35,0xbf80bec4,0xbd49bf6d,0xbf5c3dc9,0xbf04bf7f,0x3f18bef1,0x3f4e3f62,
  0x3e16bf55,0x3f7d3f0e,0x3e793f7b,0xbf78be48,0x3f2c3f75,0xbf3e3e95,0xbf67bf46,0x3edbbf22,0xbedb3f35,0xbf67bf35,0x3f3ebec4,0x3f2c3f6d,
  0xbe79bf7f,0x3f783dc9,0xbe163f62,0xbf7dbef1,0x3f4e3f55,0xbf183f0e,0xbf04bf7b,0x3f5cbe48,0xbf80be95,0xbd49bf75,0x3f713f22,0xbeac3f46,
  0xbf5cbf35,0x3f04bf35,0xbe163f6d,0xbf7dbec4,0x3f803e95,0xbd493f75,0xbeacbf7f,0x3f71bdc9,0xbf673e48,0xbedbbf7b,0x3f3e3f55,0xbf2c3f0e,
  0x3f18bf22,0x3f4e3f46,0xbf78bef1,0x3e79bf62,0x3f18bf35,0x3f4e3f35,0xbf04bf6d,0x3f5cbec4,0xbeac3f62,0xbf71bef1,0x3f3e3f46,0xbf2c3f22,
  0x3d49bf7b,0x3f803e48,0xbf67bf0e,0x3edbbf55,0x3e793f7f,0xbf783dc9,0x3f7d3e95,0xbe163f75,0x3f3e3f35,0xbf2c3f35,0x3f713ec4,0xbeac3f6d,
  0xbf4ebf22,0x3f18bf46,0xbf78be95,0x3e79bf75,0x3f5c3f0e,0xbf043f55,0x3f7d3e48,0xbe163f7b,0xbf67bef1,0x3edbbf62,0xbf80bdc9,0x3d49bf7f,
  0xbf3e3f35,0xbf2cbf35,0xbf713ec4,0xbeacbf6d,0x3f4ebf22,0x3f183f46,0x3f78be95,0x3e793f75,0xbf5c3f0e,0xbf04bf55,0xbf7d3e48,0xbe16bf7b,
  0x3f67bef1,0x3edb3f62,0x3f80bdc9,0x3d493f7f,0xbf18bf35,0x3f4ebf35,0x3f04bf6d,0x3f5c3ec4,0x3eac3f62,0xbf713ef1,0xbf3e3f46,0xbf2cbf22,
  0xbd49bf7b,0x3f80be48,0x3f67bf0e,0x3edb3f55,0xbe793f7f,0xbf78bdc9,0xbf7d3e95,0xbe16bf75,0x3f5cbf35,0x3f043f35,0x3e163f6d,0xbf7d3ec4,
  0xbf803e95,0xbd49bf75,0x3eacbf7f,0x3f713dc9,0x3f673e48,0xbedb3f7b,0xbf3e3f55,0xbf2cbf0e,0xbf18bf22,0x3f4ebf46,0x3f78bef1,0x3e793f62,
  0x3edb3f35,0xbf673f35,0xbf3ebec4,0x3f2cbf6d,0x3e79bf7f,0x3f78bdc9,0x3e163f62,0xbf7d3ef1,0xbf4e3f55,0xbf18bf0e,0x3f04bf7b,0x3f5c3e48,
  0x3f80be95,0xbd493f75,0xbf713f22,0xbeacbf46,0xbf713f35,0xbeacbf35,0x3f80bec4,0xbd493f6d,0x3f5c3dc9,0xbf043f7f,0xbf18bef1,0x3f4ebf62,
  0xbe16bf55,0x3f7dbf0e,0xbe793f7b,0xbf783e48,0xbf2c3f75,0xbf3ebe95,0x3f67bf46,0x3edb3f22,0xbe79bf35,0x3f78bf35,0xbf4e3f6d,0xbf18bec4,
  0xbf3e3f75,0xbf2cbe95,0x3f67bdc9,0xbedb3f7f,0x3f71be48,0xbeac3f7b,0xbd49bf55,0x3f80bf0e,0xbe16bf46,0x3f7dbf22,0xbf5c3f62,0xbf04bef1,
  0x3f7dbf35,0x3e163f35,0x3e79bf6d,0x3f78bec4,0xbedbbef1,0x3f67bf62,0xbf803f22,0xbd49bf46,0xbf3e3f7b,0xbf2cbe48,0x3eac3f0e,0xbf713f55,
  0x3f5cbdc9,0xbf043f7f,0x3f4ebf75,0x3f183e95,0x3d493f35,0xbf803f35,0x3edb3ec4,0xbf673f6d,0x3f7dbf46,0x3e163f22,0x3f5cbf75,0x3f043e95,
  0xbe79bf0e,0x3f78bf55,0xbf18be48,0x3f4ebf7b,0xbf713f62,0xbeacbef1,0xbf3e3f7f,0xbf2cbdc9,0xbf803f35,0x3d49bf35,0xbf673ec4,0x3edbbf6d,
  0xbe163f46,0xbf7d3f22,0xbf043f75,0xbf5c3e95,0x3f78bf0e,0xbe793f55,0x3f4ebe48,0xbf183f7b,0x3eacbf62,0x3f71bef1,0x3f2cbf7f,0x3f3ebdc9,
  0x3e16bf35,0x3f7dbf35,0x3f78bf6d,0x3e793ec4,0xbf673ef1,0x3edbbf62,0x3d49bf22,0x3f80bf46,0xbf2c3f7b,0xbf3e3e48,0xbf713f0e,0x3eacbf55,
  0x3f043dc9,0xbf5c3f7f,0xbf183f75,0xbf4e3e95,0x3f78bf35,0xbe793f35,0xbf183f6d,0xbf4e3ec4,0x3f2cbf75,0x3f3ebe95,0x3edb3dc9,0xbf673f7f,
  0xbeacbe48,0x3f71bf7b,0x3f80bf55,0xbd493f0e,0xbf7d3f46,0x3e16bf22,0x3f04bf62,0x3f5cbef1,0xbeac3f35,0xbf713f35,0xbd49bec4,0x3f80bf6d,
  0x3f04bdc9,0xbf5c3f7f,0xbf4e3ef1,0x3f18bf62,0x3f7dbf55,0xbe163f0e,0xbf783f7b,0xbe79be48,0x3f3ebf75,0x3f2cbe95,0xbedb3f46,0xbf673f22,
  0xbf673f35,0x3edbbf35,0x3f2cbec4,0xbf3e3f6d,0xbf783f7f,0xbe79bdc9,0x3f7dbf62,0xbe163ef1,0xbf183f55,0xbf4e3f0e,0x3f5cbf7b,0x3f04be48,
  0x3d493e95,0xbf803f75,0x3eacbf22,0x3f71bf46,0x3f04bf35,0x3f5cbf35,0xbf7d3f6d,0x3e16bec4,0x3d49be95,0x3f80bf75,0xbf713f7f,0xbeac3dc9,
  0xbedb3e48,0x3f67bf7b,0xbf2c3f55,0xbf3e3f0e,0xbf4e3f22,0x3f18bf46,0xbe793ef1,0xbf783f62,0x3f4ebf35,0xbf183f35,0x3f5cbf6d,0x3f04bec4,
  0x3f71bf62,0xbeac3ef1,0x3f2cbf46,0x3f3ebf22,0x3f80bf7b,0xbd493e48,0x3edbbf0e,0x3f67bf55,0x3f78bf7f,0x3e79bdc9,0x3e16be95,0x3f7dbf75,
  0xbf2c3f35,0xbf3e3f35,0xbeac3ec4,0xbf713f6d,0xbf183f22,0xbf4e3f46,0xbe793e95,0xbf783f75,0xbf043f0e,0xbf5c3f55,0xbe163e48,0xbf7d3f7b,
  0xbedb3ef1,0xbf673f62,0xbd493dc9,0xbf803f7f,0x3b003b00,0x00000000,0x80008000,0x3b00bb00,0x3b003b00,0x00000000,0x80008000,0x3b00bb00,
  0x3b003b00,0x00000000,0x80008000,0x3b00bb00,0x3b003b00,0x00000000,0x80008000,0x3b00bb00,0x3afd3b00,0x3996b8c9,0xb996b8c9,0x3afdbb00,
  0x3af13af8,0x3a2cb9f9,0xba2cb9f9,0x3af1baf8,0x3adc3ae7,0x3a84ba5b,0xba84ba5b,0x3adcbae7,0x3abe3ace,0x3aacba98,0xbaacba98,0x3abebace,
  0x3af53aff,0x3a15b949,0xba15b949,0x3af5baff,0x3ac63ae2,0x3aa2ba71,0xbaa2ba71,0x3ac6bae2,0x3a713aa2,0x3ae2bac6,0xbae2bac6,0x3a71baa2,
  0x39493a15,0x3affbaf5,0xbaffbaf5,0x3949ba15,0x3ae73afd,0x3a5bb996,0xba5bb996,0x3ae7bafd,0x3a843abe,0x3adcbaac,0xbadcbaac,0x3a84babe,
  0xb8c939f9,0x3b00baf8,0xbb00baf8,0xb8c9b9f9,0xba98ba2c,0x3acebaf1,0xbacebaf1,0xba983a2c,0x3ad53afb,0x3a8eb9c8,0xba8eb9c8,0x3ad5bafb,
  0x39c83a8e,0x3afbbad5,0xbafbbad5,0x39c8ba8e,0xba8eb9c8,0x3ad5bafb,0xbad5bafb,0xba8e39c8,0xbafbbad5,0x39c8ba8e,0xb9c8ba8e,0xbafb3ad5,
  0x3abe3af8,0x3aacb9f9,0xbaacb9f9,0x3abebaf8,0xb9963a2c,0x3afdbaf1,0xbafdbaf1,0xb996ba2c,0xbae7ba98,0x3a5bbace,0xba5bbace,0xbae73a98,
  0xbadcbb00,0xba8438c9,0x3a8438c9,0xbadc3b00,0x3aa23af5,0x3ac6ba15,0xbac6ba15,0x3aa2baf5,0xba713949,0x3ae2baff,0xbae2baff,0xba71b949,
  0xbaffbae2,0xb949ba71,0x3949ba71,0xbaff3ae2,0xba15bac6,0xbaf53aa2,0x3af53aa2,0xba153ac6,0x3a843af1,0x3adcba2c,0xbadcba2c,0x3a84baf1,
  0xbabeb996,0x3aacbafd,0xbaacbafd,0xbabe3996,0xbacebb00,0xba98b8c9,0x3a98b8c9,0xbace3b00,0x3a5bb9f9,0xbae73af8,0x3ae73af8,0x3a5b39f9,
  0x3a443aed,0x3aedba44,0xbaedba44,0x3a44baed,0xbaedba44,0x3a44baed,0xba44baed,0xbaed3a44,0xba44baed,0xbaed3a44,0x3aed3a44,0xba443aed,
  0x3aed3a44,0xba443aed,0x3a443aed,0x3aedba44,0x39f93ae7,0x3af8ba5b,0xbaf8ba5b,0x39f9bae7,0xbb00ba98,0x38c9bace,0xb8c9bace,0xbb003a98,
  0x3996baac,0xbafd3abe,0x3afd3abe,0x39963aac,0x3af13adc,0x3a2c3a84,0xba2c3a84,0x3af1badc,0x39493ae2,0x3affba71,0xbaffba71,0x3949bae2,
  0xbaf5bac6,0xba15baa2,0x3a15baa2,0xbaf53ac6,0x3aa2ba15,0xbac63af5,0x3ac63af5,0x3aa23a15,0x3a713aff,0x3ae2b949,0xbae2b949,0x3a71baff,
  0xb8c93adc,0x3b00ba84,0xbb00ba84,0xb8c9badc,0xbacebae7,0xba98ba5b,0x3a98ba5b,0xbace3ae7,0x3af13996,0xba2c3afd,0x3a2c3afd,0x3af1b996,
  0xb9f93abe,0x3af8baac,0xbaf8baac,0xb9f9babe,0xb9c83ad5,0x3afbba8e,0xbafbba8e,0xb9c8bad5,0xba8ebafb,0xbad5b9c8,0x3ad5b9c8,0xba8e3afb,
  0x3afb3a8e,0x39c83ad5,0xb9c83ad5,0x3afbba8e,0xbad539c8,0x3a8ebafb,0xba8ebafb,0xbad5b9c8,0xba2c3ace,0x3af1ba98,0xbaf1ba98,0xba2cbace,
  0xb9f9bb00,0xbaf838c9,0x3af838c9,0xb9f93b00,0x3abe3adc,0x3aac3a84,0xbaac3a84,0x3abebadc,0xbafdba5b,0xb996bae7,0x3996bae7,0xbafd3a5b,
  0xba713ac6,0x3ae2baa2,0xbae2baa2,0xba71bac6,0x3949baf5,0xbaff3a15,0x3aff3a15,0x39493af5,0x3a153aff,0x3af53949,0xbaf53949,0x3a15baff,
  0xbaa2bae2,0xbac6ba71,0x3ac6ba71,0xbaa23ae2,0xba983abe,0x3acebaac,0xbacebaac,0xba98babe,0x3a5bbadc,0xbae73a84,0x3ae73a84,0x3a5b3adc,
  0xb9f93af1,0x3af8ba2c,0xbaf8ba2c,0xb9f9baf1,0x38c9bafd,0xbb003996,0x3b003996,0x38c93afd,0xbab53ab5,0x3ab5bab5,0xbab5bab5,0xbab5bab5,
  0x3ab5bab5,0xbab53ab5,0x3ab53ab5,0x3ab53ab5,0xbab53ab5,0x3ab5bab5,0xbab5bab5,0xbab5bab5,0x3ab5bab5,0xbab53ab5,0x3ab53ab5,0x3ab53ab5,
  0xbace3aac,0x3a98babe,0xba98babe,0xbacebaac,0x3ae7ba84,0xba5b3adc,0x3a5b3adc,0x3ae73a84,0xbaf83a2c,0x39f9baf1,0xb9f9baf1,0xbaf8ba2c,
  0x3b00b996,0xb8c93afd,0x38c93afd,0x3b003996,0xbae23aa2,0x3a71bac6,0xba71bac6,0xbae2baa2,0x3affba15,0xb9493af5,0x39493af5,0x3aff3a15,
  0xbaf5b949,0xba15baff,0x3a15baff,0xbaf53949,0x3ac63a71,0x3aa23ae2,0xbaa23ae2,0x3ac6ba71,0xbaf13a98,0x3a2cbace,0xba2cbace,0xbaf1ba98,
  0x3af8b8c9,0x39f93b00,0xb9f93b00,0x3af838c9,0xbaacba84,0xbabebadc,0x3abebadc,0xbaac3a84,0x39963ae7,0x3afd3a5b,0xbafd3a5b,0x3996bae7,
  0xbafb3a8e,0x39c8bad5,0xb9c8bad5,0xbafbba8e,0x3ad539c8,0x3a8e3afb,0xba8e3afb,0x3ad5b9c8,0xb9c8bad5,0xbafbba8e,0x3afbba8e,0xb9c83ad5,
  0xba8e3afb,0x3ad5b9c8,0xbad5b9c8,0xba8ebafb,0xbb003a84,0x38c9badc,0xb8c9badc,0xbb00ba84,0x3a983a5b,0x3ace3ae7,0xbace3ae7,0x3a98ba5b,
  0x3a2cbafd,0xbaf1b996,0x3af1b996,0x3a2c3afd,0xbaf83aac,0x39f9babe,0xb9f9babe,0xbaf8baac,0xbaff3a71,0xb949bae2,0x3949bae2,0xbaffba71,
  0x3a153aa2,0x3af53ac6,0xbaf53ac6,0x3a15baa2,0x3ac6baf5,0xbaa23a15,0x3aa23a15,0x3ac63af5,0xbae23949,0xba71baff,0x3a71baff,0xbae2b949,
  0xbaf83a5b,0xb9f9bae7,0x39f9bae7,0xbaf8ba5b,0xb8c93ace,0x3b003a98,0xbb003a98,0xb8c9bace,0x3afdbabe,0xb9963aac,0x39963aac,0x3afd3abe,
  0xba2cba84,0xbaf1badc,0x3af1badc,0xba2c3a84,0xbaed3a44,0xba44baed,0x3a44baed,0xbaedba44,0xba443aed,0x3aed3a44,0xbaed3a44,0xba44baed,
  0x3aedba44,0x3a443aed,0xba443aed,0x3aed3a44,0x3a44baed,0xbaedba44,0x3aedba44,0x3a443aed,0xbadc3a2c,0xba84baf1,0x3a84baf1,0xbadcba2c,
  0xbaac3afd,0x3abe3996,0xbabe3996,0xbaacbafd,0x3a9838c9,0x3ace3b00,0xbace3b00,0x3a98b8c9,0x3ae7baf8,0xba5b39f9,0x3a5b39f9,0x3ae73af8,
  0xbac63a15,0xbaa2baf5,0x3aa2baf5,0xbac6ba15,0xbae23aff,0x3a71b949,0xba71b949,0xbae2baff,0x39493a71,0x3aff3ae2,0xbaff3ae2,0x3949ba71,
  0x3af5baa2,0x3a153ac6,0xba153ac6,0x3af53aa2,0xbaac39f9,0xbabebaf8,0x3abebaf8,0xbaacb9f9,0xbafd3af1,0x3996ba2c,0xb996ba2c,0xbafdbaf1,
  0xba5b3ace,0x3ae73a98,0xbae73a98,0xba5bbace,0x3a84b8c9,0x3adc3b00,0xbadc3b00,0x3a8438c9,0xba8e39c8,0xbad5bafb,0x3ad5bafb,0xba8eb9c8,
  0xbafb3ad5,0xb9c8ba8e,0x39c8ba8e,0xbafbbad5,0xbad53afb,0x3a8e39c8,0xba8e39c8,0xbad5bafb,0xb9c83a8e,0x3afb3ad5,0xbafb3ad5,0xb9c8ba8e,
  0xba5b3996,0xbae7bafd,0x3ae7bafd,0xba5bb996,0xbadc3aac,0xba84babe,0x3a84babe,0xbadcbaac,0xbb003af8,0x38c9b9f9,0xb8c9b9f9,0xbb00baf8,
  0xbace3af1,0x3a983a2c,0xba983a2c,0xbacebaf1,0xba153949,0xbaf5baff,0x3af5baff,0xba15b949,0xbaa23a71,0xbac6bae2,0x3ac6bae2,0xbaa2ba71,
  0xbae23ac6,0xba71baa2,0x3a71baa2,0xbae2bac6,0xbaff3af5,0xb949ba15,0x3949ba15,0xbaffbaf5,0xb99638c9,0xbafdbb00,0x3afdbb00,0xb996b8c9,
  0xba2c39f9,0xbaf1baf8,0x3af1baf8,0xba2cb9f9,0xba843a5b,0xbadcbae7,0x3adcbae7,0xba84ba5b,0xbaac3a98,0xbabebace,0x3abebace,0xbaacba98,
  0x3b003b00,0x00000000,0x80008000,0x3b00bb00,0x3b003b00,0x00000000,0x80008000,0x3b00bb00,0x3b003b00,0x00000000,0x80008000,0x3b00bb00,
  0x3b003b00,0x00000000,0x80008000,0x3b00bb00,0x3a983aac,0x3acebabe,0xbacebabe,0x3a98baac,0x3a5b3a84,0x3ae7badc,0xbae7badc,0x3a5bba84,
  0x39f93a2c,0x3af8baf1,0xbaf8baf1,0x39f9ba2c,0x38c93996,0x3b00bafd,0xbb00bafd,0x38c9b996,0xba15b949,0x3af5baff,0xbaf5baff,0xba153949,
  0xbaa2ba71,0x3ac6bae2,0xbac6bae2,0xbaa23a71,0xbae2bac6,0x3a71baa2,0xba71baa2,0xbae23ac6,0xbaffbaf5,0x3949ba15,0xb949ba15,0xbaff3af5,
  0xbaf1bace,0x3a2cba98,0xba2cba98,0xbaf13ace,0xbaf8bb00,0xb9f9b8c9,0x39f9b8c9,0xbaf83b00,0xbaacbadc,0xbabe3a84,0x3abe3a84,0xbaac3adc,
  0xb996ba5b,0xbafd3ae7,0x3afd3ae7,0xb9963a5b,0xbad5bafb,0xba8e39c8,0x3a8e39c8,0xbad53afb,0xb9c8ba8e,0xbafb3ad5,0x3afb3ad5,0xb9c83a8e,
  0x3a8e39c8,0xbad53afb,0x3ad53afb,0x3a8eb9c8,0x3afb3ad5,0xb9c83a8e,0x39c83a8e,0x3afbbad5,0xb8c9ba84,0xbb003adc,0x3b003adc,0xb8c93a84,
  0x3ace3a5b,0xba983ae7,0x3a983ae7,0x3aceba5b,0x3af13afd,0x3a2c3996,0xba2c3996,0x3af1bafd,0x39f93aac,0x3af8babe,0xbaf8babe,0x39f9baac,
  0x3ac63a15,0xbaa23af5,0x3aa23af5,0x3ac6ba15,0x3ae23aff,0x3a713949,0xba713949,0x3ae2baff,0xb9493a71,0x3affbae2,0xbaffbae2,0xb949ba71,
  0xbaf5baa2,0x3a15bac6,0xba15bac6,0xbaf53aa2,0x3af83ae7,0x39f93a5b,0xb9f93a5b,0x3af8bae7,0xb8c93a98,0x3b00bace,0xbb00bace,0xb8c9ba98,
  0xbafdbaac,0x3996babe,0xb996babe,0xbafd3aac,0xba2cbadc,0xbaf13a84,0x3af13a84,0xba2c3adc,0x3a443aed,0x3aedba44,0xbaedba44,0x3a44baed,
  0xbaedba44,0x3a44baed,0xba44baed,0xbaed3a44,0xba44baed,0xbaed3a44,0x3aed3a44,0xba443aed,0x3aed3a44,0xba443aed,0x3a443aed,0x3aedba44,
  0xba843a2c,0x3adcbaf1,0xbadcbaf1,0xba84ba2c,0xbabebafd,0xbaacb996,0x3aacb996,0xbabe3afd,0x3ace38c9,0xba983b00,0x3a983b00,0x3aceb8c9,
  0x3a5b3af8,0x3ae7b9f9,0xbae7b9f9,0x3a5bbaf8,0xbaffba71,0x3949bae2,0xb949bae2,0xbaff3a71,0x3a15baa2,0xbaf53ac6,0x3af53ac6,0x3a153aa2,
  0x3ac63af5,0x3aa23a15,0xbaa23a15,0x3ac6baf5,0xbae2b949,0x3a71baff,0xba71baff,0xbae23949,0xbaacbaf8,0xbabeb9f9,0x3abeb9f9,0xbaac3af8,
  0x3afd3a2c,0xb9963af1,0x39963af1,0x3afdba2c,0xba5b3a98,0x3ae7bace,0xbae7bace,0xba5bba98,0xba84bb00,0xbadcb8c9,0x3adcb8c9,0xba843b00,
  0x39c8bad5,0xbafb3a8e,0x3afb3a8e,0x39c83ad5,0x3a8e3afb,0x3ad539c8,0xbad539c8,0x3a8ebafb,0xbafbba8e,0xb9c8bad5,0x39c8bad5,0xbafb3a8e,
  0x3ad5b9c8,0xba8e3afb,0x3a8e3afb,0x3ad539c8,0x3ae7b996,0xba5b3afd,0x3a5b3afd,0x3ae73996,0xba843aac,0x3adcbabe,0xbadcbabe,0xba84baac,
  0xb8c9baf8,0xbb0039f9,0x3b0039f9,0xb8c93af8,0x3a983af1,0x3ace3a2c,0xbace3a2c,0x3a98baf1,0x3ae23aa2,0x3a713ac6,0xba713ac6,0x3ae2baa2,
  0xbaffba15,0xb949baf5,0x3949baf5,0xbaff3a15,0x3af5b949,0xba153aff,0x3a153aff,0x3af53949,0xbac63a71,0x3aa2bae2,0xbaa2bae2,0xbac6ba71,
  0x39963b00,0x3afd38c9,0xbafd38c9,0x3996bb00,0xba2cbaf8,0xbaf1b9f9,0x3af1b9f9,0xba2c3af8,0x3a843ae7,0x3adc3a5b,0xbadc3a5b,0x3a84bae7,
  0xbaacbace,0xbabeba98,0x3abeba98,0xbaac3ace,0xbab53ab5,0x3ab5bab5,0xbab5bab5,0xbab5bab5,0x3ab5bab5,0xbab53ab5,0x3ab53ab5,0x3ab53ab5,
  0xbab53ab5,0x3ab5bab5,0xbab5bab5,0xbab5bab5,0x3ab5bab5,0xbab53ab5,0x3ab53ab5,0x3ab53ab5,0xbafdb8c9,0xb996bb00,0x3996bb00,0xbafd38c9,
  0x3af139f9,0x3a2c3af8,0xba2c3af8,0x3af1b9f9,0xbadcba5b,0xba84bae7,0x3a84bae7,0xbadc3a5b,0x3abe3a98,0x3aac3ace,0xbaac3ace,0x3abeba98,
  0xba71bac6,0xbae2baa2,0x3ae2baa2,0xba713ac6,0x39493af5,0x3aff3a15,0xbaff3a15,0x3949baf5,0x3a15baff,0xbaf53949,0x3af53949,0x3a153aff,
  0xbaa23ae2,0x3ac6ba71,0xbac6ba71,0xbaa2bae2,0x3a5bbafd,0xbae73996,0x3ae73996,0x3a5b3afd,0xbadc3abe,0x3a84baac,0xba84baac,0xbadcbabe,
  0x3b00b9f9,0x38c93af8,0xb8c93af8,0x3b0039f9,0xbaceba2c,0xba98baf1,0x3a98baf1,0xbace3a2c,0x3afbba8e,0xb9c83ad5,0x39c83ad5,0x3afb3a8e,
  0xbad5b9c8,0xba8ebafb,0x3a8ebafb,0xbad539c8,0x39c83ad5,0x3afb3a8e,0xbafb3a8e,0x39c8bad5,0x3a8ebafb,0xbad539c8,0x3ad539c8,0x3a8e3afb,
  0x3abe39f9,0x3aac3af8,0xbaac3af8,0x3abeb9f9,0x3996baf1,0xbafdba2c,0x3afdba2c,0x39963af1,0xbae73ace,0x3a5bba98,0xba5bba98,0xbae7bace,
  0x3adc38c9,0x3a843b00,0xba843b00,0x3adcb8c9,0xb9493ae2,0x3aff3a71,0xbaff3a71,0xb949bae2,0x3af5bac6,0xba153aa2,0x3a153aa2,0x3af53ac6,
  0xbaa2ba15,0xbac6baf5,0x3ac6baf5,0xbaa23a15,0xba713aff,0x3ae23949,0xbae23949,0xba71baff,0xbadc3af1,0x3a84ba2c,0xba84ba2c,0xbadcbaf1,
  0x3aac3996,0x3abe3afd,0xbabe3afd,0x3aacb996,0x3a98bb00,0xbaceb8c9,0x3aceb8c9,0x3a983b00,0xbae739f9,0xba5bbaf8,0x3a5bbaf8,0xbae7b9f9,
  0xbaed3a44,0xba44baed,0x3a44baed,0xbaedba44,0xba443aed,0x3aed3a44,0xbaed3a44,0xba44baed,0x3aedba44,0x3a443aed,0xba443aed,0x3aed3a44,
  0x3a44baed,0xbaedba44,0x3aedba44,0x3a443aed,0xb9f9ba5b,0xbaf8bae7,0x3af8bae7,0xb9f93a5b,0xbb003ace,0x38c9ba98,0xb8c9ba98,0xbb00bace,
  0xb9963abe,0x3afd3aac,0xbafd3aac,0xb996babe,0x3af1ba84,0x3a2c3adc,0xba2c3adc,0x3af13a84,0x3aa2baf5,0xbac6ba15,0x3ac6ba15,0x3aa23af5,
  0xba71b949,0xbae2baff,0x3ae2baff,0xba713949,0xbaff3ae2,0x3949ba71,0xb949ba71,0xbaffbae2,0xba153ac6,0x3af53aa2,0xbaf53aa2,0xba15bac6,
  0x3b00badc,0x38c93a84,0xb8c93a84,0x3b003adc,0x3a98bae7,0xbaceba5b,0x3aceba5b,0x3a983ae7,0xba2cb996,0xbaf1bafd,0x3af1bafd,0xba2c3996,
  0xbaf83abe,0xb9f9baac,0x39f9baac,0xbaf8babe,0x3a8eb9c8,0x3ad53afb,0xbad53afb,0x3a8e39c8,0x3afbbad5,0x39c83a8e,0xb9c83a8e,0x3afb3ad5,
  0x3ad5bafb,0xba8eb9c8,0x3a8eb9c8,0x3ad53afb,0x39c8ba8e,0xbafbbad5,0x3afbbad5,0x39c83a8e,0xba2c3a98,0x3af13ace,0xbaf13ace,0xba2cba98,
  0x39f938c9,0x3af83b00,0xbaf83b00,0x39f9b8c9,0x3abeba84,0x3aac3adc,0xbaac3adc,0x3abe3a84,0x3afdbae7,0x39963a5b,0xb9963a5b,0x3afd3ae7,
  0xbaf53aff,0x3a153949,0xba153949,0xbaf5baff,0xbac63ae2,0x3aa23a71,0xbaa23a71,0xbac6bae2,0xba713aa2,0x3ae23ac6,0xbae23ac6,0xba71baa2,
  0xb9493a15,0x3aff3af5,0xbaff3af5,0xb949ba15,0xbace3abe,0xba98baac,0x3a98baac,0xbacebabe,0xbae73adc,0xba5bba84,0x3a5bba84,0xbae7badc,
  0xbaf83af1,0xb9f9ba2c,0x39f9ba2c,0xbaf8baf1,0xbb003afd,0xb8c9b996,0x38c9b996,0xbb00bafd,0x3b003b00,0x00000000,0x80008000,0x3b00bb00,
  0x3b003b00,0x00000000,0x80008000,0x3b00bb00,0x3b003b00,0x00000000,0x80008000,0x3b00bb00,0x3b003b00,0x00000000,0x80008000,0x3b00bb00,
  0xb996b8c9,0x3afdbb00,0xbafdbb00,0xb99638c9,0xba2cb9f9,0x3af1baf8,0xbaf1baf8,0xba2c39f9,0xba84ba5b,0x3adcbae7,0xbadcbae7,0xba843a5b,
  0xbaacba98,0x3abebace,0xbabebace,0xbaac3a98,0xbaf5baff,0xba153949,0x3a153949,0xbaf53aff,0xbac6bae2,0xbaa23a71,0x3aa23a71,0xbac63ae2,
  0xba71baa2,0xbae23ac6,0x3ae23ac6,0xba713aa2,0xb949ba15,0xbaff3af5,0x3aff3af5,0xb9493a15,0x3a5b3996,0xbae73afd,0x3ae73afd,0x3a5bb996,
  0x3adc3aac,0xba843abe,0x3a843abe,0x3adcbaac,0x3b003af8,0x38c939f9,0xb8c939f9,0x3b00baf8,0x3ace3af1,0x3a98ba2c,0xba98ba2c,0x3acebaf1,
  0x3ad53afb,0x3a8eb9c8,0xba8eb9c8,0x3ad5bafb,0x39c83a8e,0x3afbbad5,0xbafbbad5,0x39c8ba8e,0xba8eb9c8,0x3ad5bafb,0xbad5bafb,0xba8e39c8,
  0xbafbbad5,0x39c8ba8e,0xb9c8ba8e,0xbafb3ad5,0xbaacb9f9,0x3abebaf8,0xbabebaf8,0xbaac39f9,0xbafdbaf1,0xb996ba2c,0x3996ba2c,0xbafd3af1,
  0xba5bbace,0xbae73a98,0x3ae73a98,0xba5b3ace,0x3a8438c9,0xbadc3b00,0x3adc3b00,0x3a84b8c9,0xbaa2baf5,0xbac63a15,0x3ac63a15,0xbaa23af5,
  0x3a71b949,0xbae23aff,0x3ae23aff,0x3a713949,0x3aff3ae2,0x39493a71,0xb9493a71,0x3affbae2,0x3a153ac6,0x3af5baa2,0xbaf5baa2,0x3a15bac6,
  0x3adc3a2c,0xba843af1,0x3a843af1,0x3adcba2c,0x3aac3afd,0x3abeb996,0xbabeb996,0x3aacbafd,0xba9838c9,0x3acebb00,0xbacebb00,0xba98b8c9,
  0xbae7baf8,0xba5bb9f9,0x3a5bb9f9,0xbae73af8,0x3a443aed,0x3aedba44,0xbaedba44,0x3a44baed,0xbaedba44,0x3a44baed,0xba44baed,0xbaed3a44,
  0xba44baed,0xbaed3a44,0x3aed3a44,0xba443aed,0x3aed3a44,0xba443aed,0x3a443aed,0x3aedba44,0xbaf8ba5b,0x39f9bae7,0xb9f9bae7,0xbaf83a5b,
  0xb8c9bace,0xbb003a98,0x3b003a98,0xb8c93ace,0x3afd3abe,0x39963aac,0xb9963aac,0x3afdbabe,0xba2c3a84,0x3af1badc,0xbaf1badc,0xba2cba84,
  0xb949bae2,0xbaff3a71,0x3aff3a71,0xb9493ae2,0x3af53ac6,0x3a153aa2,0xba153aa2,0x3af5bac6,0xbaa23a15,0x3ac6baf5,0xbac6baf5,0xbaa2ba15,
  0xba71baff,0xbae23949,0x3ae23949,0xba713aff,0x3b003a84,0x38c93adc,0xb8c93adc,0x3b00ba84,0xba983a5b,0x3acebae7,0xbacebae7,0xba98ba5b,
  0xba2cbafd,0xbaf13996,0x3af13996,0xba2c3afd,0x3af83aac,0x39f93abe,0xb9f93abe,0x3af8baac,0xb9c83ad5,0x3afbba8e,0xbafbba8e,0xb9c8bad5,
  0xba8ebafb,0xbad5b9c8,0x3ad5b9c8,0xba8e3afb,0x3afb3a8e,0x39c83ad5,0xb9c83ad5,0x3afbba8e,0xbad539c8,0x3a8ebafb,0xba8ebafb,0xbad5b9c8,
  0xbaf1ba98,0xba2cbace,0x3a2cbace,0xbaf13a98,0x3af838c9,0xb9f93b00,0x39f93b00,0x3af8b8c9,0xbaac3a84,0x3abebadc,0xbabebadc,0xbaacba84,
  0x3996bae7,0xbafd3a5b,0x3afd3a5b,0x39963ae7,0x3a71bac6,0xbae23aa2,0x3ae23aa2,0x3a713ac6,0xb9493af5,0x3affba15,0xbaffba15,0xb949baf5,
  0xba15baff,0xbaf5b949,0x3af5b949,0xba153aff,0x3aa23ae2,0x3ac63a71,0xbac63a71,0x3aa2bae2,0x3ace3aac,0x3a983abe,0xba983abe,0x3acebaac,
  0xbae7ba84,0xba5bbadc,0x3a5bbadc,0xbae73a84,0x3af83a2c,0x39f93af1,0xb9f93af1,0x3af8ba2c,0xbb00b996,0xb8c9bafd,0x38c9bafd,0xbb003996,
  0xbab53ab5,0x3ab5bab5,0xbab5bab5,0xbab5bab5,0x3ab5bab5,0xbab53ab5,0x3ab53ab5,0x3ab53ab5,0xbab53ab5,0x3ab5bab5,0xbab5bab5,0xbab5bab5,
  0x3ab5bab5,0xbab53ab5,0x3ab53ab5,0x3ab53ab5,0xba98babe,0xbacebaac,0x3acebaac,0xba983abe,0x3a5b3adc,0x3ae73a84,0xbae73a84,0x3a5bbadc,
  0xb9f9baf1,0xbaf8ba2c,0x3af8ba2c,0xb9f93af1,0x38c93afd,0x3b003996,0xbb003996,0x38c9bafd,0x3ae2baa2,0xba713ac6,0x3a713ac6,0x3ae23aa2,
  0xbaff3a15,0x3949baf5,0xb949baf5,0xbaffba15,0x3af53949,0x3a153aff,0xba153aff,0x3af5b949,0xbac6ba71,0xbaa2bae2,0x3aa2bae2,0xbac63a71,
  0x3a2c3ace,0x3af13a98,0xbaf13a98,0x3a2cbace,0x39f9bb00,0xbaf8b8c9,0x3af8b8c9,0x39f93b00,0xbabe3adc,0x3aacba84,0xbaacba84,0xbabebadc,
  0x3afdba5b,0xb9963ae7,0x39963ae7,0x3afd3a5b,0xbafb3a8e,0x39c8bad5,0xb9c8bad5,0xbafbba8e,0x3ad539c8,0x3a8e3afb,0xba8e3afb,0x3ad5b9c8,
  0xb9c8bad5,0xbafbba8e,0x3afbba8e,0xb9c83ad5,0xba8e3afb,0x3ad5b9c8,0xbad5b9c8,0xba8ebafb,0xb8c9badc,0xbb00ba84,0x3b00ba84,0xb8c93adc,
  0xbace3ae7,0x3a98ba5b,0xba98ba5b,0xbacebae7,0x3af1b996,0x3a2c3afd,0xba2c3afd,0x3af13996,0xb9f9babe,0xbaf8baac,0x3af8baac,0xb9f93abe,
  0x3affba71,0x39493ae2,0xb9493ae2,0x3aff3a71,0xba15baa2,0xbaf5bac6,0x3af5bac6,0xba153aa2,0xbac63af5,0x3aa2ba15,0xbaa2ba15,0xbac6baf5,
  0x3ae2b949,0x3a713aff,0xba713aff,0x3ae23949,0xb9f93ae7,0x3af83a5b,0xbaf83a5b,0xb9f9bae7,0x3b00ba98,0x38c93ace,0xb8c93ace,0x3b003a98,
  0xb996baac,0xbafdbabe,0x3afdbabe,0xb9963aac,0xbaf13adc,0x3a2cba84,0xba2cba84,0xbaf1badc,0xbaed3a44,0xba44baed,0x3a44baed,0xbaedba44,
  0xba443aed,0x3aed3a44,0xbaed3a44,0xba44baed,0x3aedba44,0x3a443aed,0xba443aed,0x3aed3a44,0x3a44baed,0xbaedba44,0x3aedba44,0x3a443aed,
  0x3a84baf1,0xbadcba2c,0x3adcba2c,0x3a843af1,0xbabe3996,0xbaacbafd,0x3aacbafd,0xbabeb996,0xbace3b00,0x3a98b8c9,0xba98b8c9,0xbacebb00,
  0x3a5b39f9,0x3ae73af8,0xbae73af8,0x3a5bb9f9,0x3ac6ba15,0x3aa23af5,0xbaa23af5,0x3ac63a15,0x3ae2baff,0xba713949,0x3a713949,0x3ae23aff,
  0xb949ba71,0xbaffbae2,0x3affbae2,0xb9493a71,0xbaf53aa2,0xba15bac6,0x3a15bac6,0xbaf5baa2,0xbabe3af8,0x3aac39f9,0xbaac39f9,0xbabebaf8,
  0x39963a2c,0x3afd3af1,0xbafd3af1,0x3996ba2c,0x3ae7ba98,0x3a5b3ace,0xba5b3ace,0x3ae73a98,0x3adcbb00,0xba84b8c9,0x3a84b8c9,0x3adc3b00,
  0xba8e39c8,0xbad5bafb,0x3ad5bafb,0xba8eb9c8,0xbafb3ad5,0xb9c8ba8e,0x39c8ba8e,0xbafbbad5,0xbad53afb,0x3a8e39c8,0xba8e39c8,0xbad5bafb,
  0xb9c83a8e,0x3afb3ad5,0xbafb3ad5,0xb9c8ba8e,0x3ae7bafd,0xba5bb996,0x3a5bb996,0x3ae73afd,0x3a84babe,0xbadcbaac,0x3adcbaac,0x3a843abe,
  0xb8c9b9f9,0xbb00baf8,0x3b00baf8,0xb8c939f9,0xba983a2c,0xbacebaf1,0x3acebaf1,0xba98ba2c,0x3a15b949,0x3af53aff,0xbaf53aff,0x3a153949,
  0x3aa2ba71,0x3ac63ae2,0xbac63ae2,0x3aa23a71,0x3ae2bac6,0x3a713aa2,0xba713aa2,0x3ae23ac6,0x3affbaf5,0x39493a15,0xb9493a15,0x3aff3af5,
  0xbafd3b00,0x399638c9,0xb99638c9,0xbafdbb00,0xbaf13af8,0x3a2c39f9,0xba2c39f9,0xbaf1baf8,0xbadc3ae7,0x3a843a5b,0xba843a5b,0xbadcbae7,
  0xbabe3ace,0x3aac3a98,0xbaac3a98,0xbabebace,0x3b003b00,0x00000000,0x80008000,0x3b00bb00,0x3b003b00,0x00000000,0x80008000,0x3b00bb00,
  0x3b003b00,0x00000000,0x80008000,0x3b00bb00,0x3b003b00,0x00000000,0x80008000,0x3b00bb00,0xbacebabe,0x3a98baac,0xba98baac,0xbace3abe,
  0xbae7badc,0x3a5bba84,0xba5bba84,0xbae73adc,0xbaf8baf1,0x39f9ba2c,0xb9f9ba2c,0xbaf83af1,0xbb00bafd,0x38c9b996,0xb8c9b996,0xbb003afd,
  0x3a153949,0xbaf53aff,0x3af53aff,0x3a15b949,0x3aa23a71,0xbac63ae2,0x3ac63ae2,0x3aa2ba71,0x3ae23ac6,0xba713aa2,0x3a713aa2,0x3ae2bac6,
  0x3aff3af5,0xb9493a15,0x39493a15,0x3affbaf5,0x3a2c3a98,0x3af1bace,0xbaf1bace,0x3a2cba98,0xb9f938c9,0x3af8bb00,0xbaf8bb00,0xb9f9b8c9,
  0xbabeba84,0x3aacbadc,0xbaacbadc,0xbabe3a84,0xbafdbae7,0x3996ba5b,0xb996ba5b,0xbafd3ae7,0xbad5bafb,0xba8e39c8,0x3a8e39c8,0xbad53afb,
  0xb9c8ba8e,0xbafb3ad5,0x3afb3ad5,0xb9c83a8e,0x3a8e39c8,0xbad53afb,0x3ad53afb,0x3a8eb9c8,0x3afb3ad5,0xb9c83a8e,0x39c83a8e,0x3afbbad5,
  0x3b003adc,0xb8c93a84,0x38c93a84,0x3b00badc,0x3a983ae7,0x3aceba5b,0xbaceba5b,0x3a98bae7,0xba2c3996,0x3af1bafd,0xbaf1bafd,0xba2cb996,
  0xbaf8babe,0x39f9baac,0xb9f9baac,0xbaf83abe,0xbac6ba15,0x3aa2baf5,0xbaa2baf5,0xbac63a15,0xbae2baff,0xba71b949,0x3a71b949,0xbae23aff,
  0x3949ba71,0xbaff3ae2,0x3aff3ae2,0x39493a71,0x3af53aa2,0xba153ac6,0x3a153ac6,0x3af5baa2,0x39f9ba5b,0xbaf83ae7,0x3af83ae7,0x39f93a5b,
  0x3b003ace,0x38c93a98,0xb8c93a98,0x3b00bace,0x39963abe,0x3afdbaac,0xbafdbaac,0x3996babe,0xbaf1ba84,0x3a2cbadc,0xba2cbadc,0xbaf13a84,
  0x3a443aed,0x3aedba44,0xbaedba44,0x3a44baed,0xbaedba44,0x3a44baed,0xba44baed,0xbaed3a44,0xba44baed,0xbaed3a44,0x3aed3a44,0xba443aed,
  0x3aed3a44,0xba443aed,0x3a443aed,0x3aedba44,0xbadcbaf1,0xba84ba2c,0x3a84ba2c,0xbadc3af1,0x3aacb996,0xbabe3afd,0x3abe3afd,0x3aac3996,
  0x3a983b00,0x3aceb8c9,0xbaceb8c9,0x3a98bb00,0xbae7b9f9,0x3a5bbaf8,0xba5bbaf8,0xbae739f9,0x3aff3a71,0xb9493ae2,0x39493ae2,0x3affba71,
  0xba153aa2,0x3af5bac6,0xbaf5bac6,0xba15baa2,0xbac6baf5,0xbaa2ba15,0x3aa2ba15,0xbac63af5,0x3ae23949,0xba713aff,0x3a713aff,0x3ae2b949,
  0xbabe39f9,0x3aacbaf8,0xbaacbaf8,0xbabeb9f9,0xb996baf1,0xbafd3a2c,0x3afd3a2c,0xb9963af1,0x3ae73ace,0x3a5b3a98,0xba5b3a98,0x3ae7bace,
  0xbadc38c9,0x3a84bb00,0xba84bb00,0xbadcb8c9,0x39c8bad5,0xbafb3a8e,0x3afb3a8e,0x39c83ad5,0x3a8e3afb,0x3ad539c8,0xbad539c8,0x3a8ebafb,
  0xbafbba8e,0xb9c8bad5,0x39c8bad5,0xbafb3a8e,0x3ad5b9c8,0xba8e3afb,0x3a8e3afb,0x3ad539c8,0x3a5b3afd,0x3ae73996,0xbae73996,0x3a5bbafd,
  0xbadcbabe,0xba84baac,0x3a84baac,0xbadc3abe,0x3b0039f9,0xb8c93af8,0x38c93af8,0x3b00b9f9,0xbace3a2c,0x3a98baf1,0xba98baf1,0xbaceba2c,
  0xbae2baa2,0xba71bac6,0x3a71bac6,0xbae23aa2,0x3aff3a15,0x39493af5,0xb9493af5,0x3affba15,0xbaf53949,0x3a15baff,0xba15baff,0xbaf5b949,
  0x3ac6ba71,0xbaa23ae2,0x3aa23ae2,0x3ac63a71,0x3afdb8c9,0xb9963b00,0x39963b00,0x3afd38c9,0xbaf139f9,0x3a2cbaf8,0xba2cbaf8,0xbaf1b9f9,
  0x3adcba5b,0xba843ae7,0x3a843ae7,0x3adc3a5b,0xbabe3a98,0x3aacbace,0xbaacbace,0xbabeba98,0xbab53ab5,0x3ab5bab5,0xbab5bab5,0xbab5bab5,
  0x3ab5bab5,0xbab53ab5,0x3ab53ab5,0x3ab53ab5,0xbab53ab5,0x3ab5bab5,0xbab5bab5,0xbab5bab5,0x3ab5bab5,0xbab53ab5,0x3ab53ab5,0x3ab53ab5,
  0x3996bb00,0xbafd38c9,0x3afd38c9,0x39963b00,0xba2c3af8,0x3af1b9f9,0xbaf1b9f9,0xba2cbaf8,0x3a84bae7,0xbadc3a5b,0x3adc3a5b,0x3a843ae7,
  0xbaac3ace,0x3abeba98,0xbabeba98,0xbaacbace,0x3a713ac6,0x3ae23aa2,0xbae23aa2,0x3a71bac6,0xb949baf5,0xbaffba15,0x3affba15,0xb9493af5,
  0xba153aff,0x3af5b949,0xbaf5b949,0xba15baff,0x3aa2bae2,0xbac63a71,0x3ac63a71,0x3aa23ae2,0xbae7b996,0xba5bbafd,0x3a5bbafd,0xbae73996,
  0x3a843aac,0x3adc3abe,0xbadc3abe,0x3a84baac,0x38c9baf8,0xbb00b9f9,0x3b00b9f9,0x38c93af8,0xba983af1,0x3aceba2c,0xbaceba2c,0xba98baf1,
  0x3afbba8e,0xb9c83ad5,0x39c83ad5,0x3afb3a8e,0xbad5b9c8,0xba8ebafb,0x3a8ebafb,0xbad539c8,0x39c83ad5,0x3afb3a8e,0xbafb3a8e,0x39c8bad5,
  0x3a8ebafb,0xbad539c8,0x3ad539c8,0x3a8e3afb,0xbaac3af8,0x3abeb9f9,0xbabeb9f9,0xbaacbaf8,0x3afdba2c,0x39963af1,0xb9963af1,0x3afd3a2c,
  0xba5bba98,0xbae7bace,0x3ae7bace,0xba5b3a98,0xba843b00,0x3adcb8c9,0xbadcb8c9,0xba84bb00,0x3949bae2,0xbaffba71,0x3affba71,0x39493ae2,
  0xbaf53ac6,0x3a15baa2,0xba15baa2,0xbaf5bac6,0x3aa23a15,0x3ac63af5,0xbac63af5,0x3aa2ba15,0x3a71baff,0xbae2b949,0x3ae2b949,0x3a713aff,
  0x3a843a2c,0x3adc3af1,0xbadc3af1,0x3a84ba2c,0x3abebafd,0xbaac3996,0x3aac3996,0x3abe3afd,0xbace38c9,0xba98bb00,0x3a98bb00,0xbaceb8c9,
  0xba5b3af8,0x3ae739f9,0xbae739f9,0xba5bbaf8,0xbaed3a44,0xba44baed,0x3a44baed,0xbaedba44,0xba443aed,0x3aed3a44,0xbaed3a44,0xba44baed,
  0x3aedba44,0x3a443aed,0xba443aed,0x3aed3a44,0x3a44baed,0xbaedba44,0x3aedba44,0x3a443aed,0x3af8bae7,0xb9f93a5b,0x39f93a5b,0x3af83ae7,
  0xb8c9ba98,0xbb00bace,0x3b00bace,0xb8c93a98,0xbafd3aac,0xb996babe,0x3996babe,0xbafdbaac,0xba2c3adc,0x3af13a84,0xbaf13a84,0xba2cbadc,
  0xbaa23af5,0x3ac63a15,0xbac63a15,0xbaa2baf5,0x3a713949,0x3ae23aff,0xbae23aff,0x3a71b949,0x3affbae2,0xb9493a71,0x39493a71,0x3aff3ae2,
  0x3a15bac6,0xbaf5baa2,0x3af5baa2,0x3a153ac6,0x38c9ba84,0xbb00badc,0x3b00badc,0x38c93a84,0xbace3a5b,0xba98bae7,0x3a98bae7,0xbaceba5b,
  0xbaf13afd,0x3a2cb996,0xba2cb996,0xbaf1bafd,0xb9f93aac,0x3af83abe,0xbaf83abe,0xb9f9baac,0x3a8eb9c8,0x3ad53afb,0xbad53afb,0x3a8e39c8,
  0x3afbbad5,0x39c83a8e,0xb9c83a8e,0x3afb3ad5,0x3ad5bafb,0xba8eb9c8,0x3a8eb9c8,0x3ad53afb,0x39c8ba8e,0xbafbbad5,0x3afbbad5,0x39c83a8e,
  0xbaf13ace,0xba2cba98,0x3a2cba98,0xbaf1bace,0xbaf83b00,0x39f9b8c9,0xb9f9b8c9,0xbaf8bb00,0xbaac3adc,0x3abe3a84,0xbabe3a84,0xbaacbadc,
  0xb9963a5b,0x3afd3ae7,0xbafd3ae7,0xb996ba5b,0x3af5baff,0xba15b949,0x3a15b949,0x3af53aff,0x3ac6bae2,0xbaa2ba71,0x3aa2ba71,0x3ac63ae2,
  0x3a71baa2,0xbae2bac6,0x3ae2bac6,0x3a713aa2,0x3949ba15,0xbaffbaf5,0x3affbaf5,0x39493a15,0xba983aac,0x3ace3abe,0xbace3abe,0xba98baac,
  0xba5b3a84,0x3ae73adc,0xbae73adc,0xba5bba84,0xb9f93a2c,0x3af83af1,0xbaf83af1,0xb9f9ba2c,0xb8c93996,0x3b003afd,0xbb003afd,0xb8c9b996,
  0x3f800000,0x3f7fffb1,0x3f7fec43,0x3f7fe705,0x3f7ffec4,0x3f7ffd39,0x3f7fe129,0x3f7fdaaf,0x3f7ffb11,0x3f7ff84a,0x3f7fd397,0x3f7fcbe2,
  0x3f7ff4e6,0x3f7ff0e3,0x3f7fc38f,0x3f7fba9e,0x3f800000,0x3f7ffd39,0x3f7f4e6d,0x3f7f1f49,0x3f7ff4e6,0x3f7fe705,0x3f7eea9d,0x3f7eb069,
  0x3f7fd397,0x3f7fba9e,0x3f7e70b0,0x3f7e2b72,0x3f7f9c18,0x3f7f7808,0x3f7de0b1,0x3f7d906e,0x3f800000,0x3f7ff84a,0x3f7e1324,0x3f7d906e,
  0x3f7fe129,0x3f7fba9e,0x3f7cfe73,0x3f7c5d3a,0x3f7f84ab,0x3f7f3f54,0x3f7baccd,0x3f7aed37,0x3f7eea9d,0x3f7e868b,0x3f7a1e84,0x3f7940c0,
  0x3f800000,0x3f7ff0e3,0x3f7c3b28,0x3f7b3bab,0x3f7fc38f,0x3f7f7808,0x3f7a1e84,0x3f78e3d6,0x3f7f0e58,0x3f7e868b,0x3f778bc5,0x3f76167a,
  0x3f7de0b1,0x3f7d1cdd,0x3f748422,0x3f72d4eb,0x3f800000,0x3f7fe705,0x3f79c79d,0x3f7822d1,0x3f7f9c18,0x3f7f1f49,0x3f764d97,0x3f74484b,
  0x3f7e70b0,0x3f7d906e,0x3f721352,0x3f6faf1b,0x3f7c7eb0,0x3f7b3bab,0x3f6d1c1d,0x3f6a5ad9,0x3f800000,0x3f7fdaaf,0x3f76ba07,0x3f74484b,
  0x3f7f6ac7,0x3f7eb069,0x3f718f57,0x3f6e8ff8,0x3f7dabcc,0x3f7c5d3a,0x3f6b4b0c,0x3f67c187,0x3f7ac516,0x3f78e3d6,0x3f63f473,0x3f5fe4e9,
  0x3f800000,0x3f7fcbe2,0x3f731447,0x3f6faf1b,0x3f7f2f9d,0x3f7e2b72,0x3f6be858,0x3f67c187,0x3f7cbfc9,0x3f7aed37,0x3f633c5a,0x3f5e5aa6,
  0x3f78b47b,0x3f76167a,0x3f591e6a,0x3f5389c7,0x3f800000,0x3f7fba9e,0x3f6ed89e,0x3f6a5ad9,0x3f7eea9d,0x3f7d906e,0x3f655e0b,0x3f5fe4e9,
  0x3f7baccd,0x3f7940c0,0x3f59f26a,0x3f5389c7,0x3f764d97,0x3f72d4eb,0x3f4cae79,0x3f456439,0x3f800000,0x3f7fa6e3,0x3f6a09a7,0x3f644fac,
  0x3f7e9bc9,0x3f7cdf6c,0x3f5df6be,0x3f570348,0x3f7a7302,0x3f77583a,0x3f4f7a1f,0x3f476085,0x3f73913f,0x3f6f20b0,0x3f3ebc1b,0x3f3592e7,
  0x3f800000,0x3f7f90b1,0x3f64aa59,0x3f5d924d,0x3f7e4323,0x3f7c187a,0x3f55b993,0x3f4d26fd,0x3f791298,0x3f75341d,0x3f43e200,0x3f39f2ac,
  0x3f708066,0x3f6afb8c,0x3f2f61a5,0x3f24381a,0x3f800000,0x3f7f7808,0x3f5ebe05,0x3f5627fe,0x3f7de0b1,0x3f7b3bab,0x3f4cae79,0x3f425b89,
  0x3f778bc5,0x3f72d4eb,0x3f373a23,0x3f2b561b,0x3f6d1c1d,0x3f666771,0x3f1ebc12,0x3f11796b,0x3f800000,0x3f7f5ce9,0x3f584853,0x3f4e1689,
  0x3f7d7474,0x3f7a4910,0x3f42de29,0x3f36ad7f,0x3f75dec6,0x3f703b37,0x3f299415,0x3f1ba299,0x3f696591,0x3f61668a,0x3f0cead0,0x3efafef7,
  0x3f800000,0x3f7f3f54,0x3f514d3d,0x3f456439,0x3f7cfe73,0x3f7940c0,0x3f385216,0x3f2a2a80,0x3f740bdd,0x3f6d67a1,0x3f1b02c6,0x3f0af1b7,
  0x3f655e0b,0x3f5bfb34,0x3ef41f07,0x3ed0eb2a,0x3f800000,0x3f7f1f49,0x3f49d112,0x3f3c17d9,0x3f7c7eb0,0x3f7822d1,0x3f2d1469,0x3f1ce11f,
  0x3f721352,0x3f6a5ad9,0x3f0b9a6b,0x3ef2bd43,0x3f6106f2,0x3f5627fe,0x3ecc9b8b,0x3ea5129f,0x3f800000,0x3f7efcc9,0x3f41d870,0x3f3238aa,
  0x3f7bf531,0x3f76ef5b,0x3f212ff9,0x3f0ee0db,0x3f6ff573,0x3f671599,0x3ef6e0cb,0x3ece0bea,0x3f5c61c7,0x3f4fefa8,0x3ea395c5,0x3e6fa8b2,
  0x3f800000,0x3f7ed7d4,0x3f396842,0x3f27ce61,0x3f7b61fc,0x3f75a67b,0x3f14b039,0x3f003a06,0x3f6db293,0x3f6398ac,0x3ed53641,0x3ea80b1f,
  0x3f577026,0x3f495521,0x3e72b651,0x3e1324ca,0x3f800000,0x3f7eb069,0x3f3085bb,0x3f1ce11f,0x3f7ac516,0x3f74484b,0x3f07a136,0x3ee1fb6a,
  0x3f6b4b0c,0x3f5fe4e9,0x3eb263ef,0x3e80f8c0,0x3f5233c6,0x3f425b89,0x3e1c76de,0x3d55880e,0x3f800000,0x3f7e868b,0x3f273656,0x3f11796b,
  0x3f7a1e84,0x3f72d4eb,0x3ef41f07,0x3ec27b55,0x3f68bf3c,0x3f5bfb34,0x3e8e9a22,0x3e3228d4,0x3f4cae79,0x3f3b0629,0x3d8a200a,0xbd2351cb,
  0x3f800000,0x3f7e5a38,0x3f1d7fd1,0x3f05a02c,0x3f796e4e,0x3f714c7a,0x3ed8106b,0x3ea21887,0x3f660f88,0x3f57dc7f,0x3e541501,0x3dc27c39,
  0x3f46e22a,0x3f33587a,0xbc96c9b6,0xbe06b26e,0x3f800000,0x3f7e2b72,0x3f13682a,0x3ef2bd43,0x3f78b47b,0x3f6faf1b,0x3ebb31a0,0x3e80f8c0,
  0x3f633c5a,0x3f5389c7,0x3e09cf86,0x3c7b514b,0x3f40d0da,0x3f2b561b,0xbdd53db9,0xbe636c83,0x3f800000,0x3f7dfa38,0x3f08f59b,0x3ed97cb9,
  0x3f77f110,0x3f6dfcf2,0x3e9d9e78,0x3e3e853e,0x3f604621,0x3f4f0417,0x3d7b2b74,0xbd83db0a,0x3f3a7ca4,0x3f2302d3,0xbe419b37,0xbe9f1cdf,
  0x3f800000,0x3f7dc68c,0x3efc5d27,0x3ebf926f,0x3f772417,0x3f6c3624,0x3e7ee6e1,0x3df475c0,0x3f5d2d53,0x3f4a4c87,0xbc490e90,0xbe1324ca,
  0x3f33e7bc,0x3f1a6293,0xbe8b9507,0xbecb2aae,0x3f800000,0x3f7d906e,0x3ee63375,0x3ea5129f,0x3f764d97,0x3f6a5ad9,0x3e419b37,0x3d55880e,
  0x3f59f26a,0x3f456439,0xbdafb680,0xbe636c83,0x3f2d1469,0x3f11796b,0xbeb554ec,0xbef58035,0x3f800000,0x3f7d57de,0x3ecf7bca,0x3e8a11f7,
  0x3f756d97,0x3f686b39,0x3e039502,0xbc7b514b,0x3f5695e5,0x3f404c5c,0xbe22abb6,0xbe9920fe,0x3f26050a,0x3f084b92,0xbeddbe79,0xbf0ee0db,
  0x3f800000,0x3f7d1cdd,0x3eb8442a,0x3e5d4b1a,0x3f748422,0x3f666771,0x3d8a200a,0xbda973ba,0x3f531849,0x3f3b0629,0xbe6c9a7f,0xbebf926f,
  0x3f1ebc12,0x3efdbabb,0xbf0242b1,0xbf21cbfb,0x3f800000,0x3f7cdf6c,0x3ea09ae5,0x3e25c58c,0x3f73913f,0x3f644fac,0x3bc90f88,0xbe195be0,
  0x3f4f7a1f,0x3f3592e7,0xbe9aa086,0xbee4cbfe,0x3f173c07,0x3eea6681,0xbf14b039,0xbf33587a,0x3f800000,0x3f7c9f8a,0x3e888e93,0x3ddb7d37,
  0x3f7294f8,0x3f62241a,0xbd621469,0xbe5d4b1a,0x3f4bbbf8,0x3f2ff3e6,0xbebe1d4a,0xbf044889,0x3f0f8784,0x3ed6a399,0xbf26050a,0xbf436051,
  0x3f800000,0x3f7c5d3a,0x3e605c13,0x3d55880e,0x3f718f57,0x3f5fe4e9,0xbdee3876,0xbe901c2c,0x3f47de65,0x3f2a2a80,0xbee0924f,0xbf1553b7,
  0x3f07a136,0x3ec27b55,0xbf36206c,0xbf51c0c2,0x3f800000,0x3f7c187a,0x3e2f10a2,0xbb490fc6,0x3f708066,0x3f5d924d,0xbe354098,0xbeb0eacb,
  0x3f43e200,0x3f24381a,0xbf00e7e4,0xbf256bcb,0x3eff17b2,0x3eadf73c,0xbf44e3f5,0xbf5e5aa6,0x3f800000,0x3f7bd14d,0x3dfab273,0xbd6ea038,
  0x3f6f6830,0x3f5b2c79,0xbe72b651,0xbed0eb2a,0x3f3fc767,0x3f1e1e22,0xbf10d3cd,0xbf34768f,0x3eee9479,0x3e9920fe,0xbf5233c6,0xbf6912ae,
  0x3f800000,0x3f7b87b2,0x3d96a905,0xbde7fa9a,0x3f6e46be,0x3f58b3a1,0xbe97a117,0xbeeff7fb,0x3f3b8f3b,0x3f17de12,0xbf1ff6cb,0xbf425b89,
  0x3eddbe79,0x3e840270,0xbf5df6be,0xbf71d19f,0x3f800000,0x3f7b3bab,0x3cc90ab0,0xbe2bf804,0x3f6d1c1d,0x3f5627fe,0xbeb554ec,0xbf06f686,
  0x3f373a23,0x3f11796b,0xbf2e3bde,0xbf4f0417,0x3ecc9b8b,0x3e5d4b1a,0xbf6816a8,0xbf788486,0x80000000,0xbb490fc6,0xbcc90ab0,0xbce22a7a,
  0xbbc90f88,0xbc16cb58,0xbcfb49ba,0xbd0a342f,0xbc490e90,0xbc7b514b,0xbd16c32c,0xbd2351cb,0xbc96c9b6,0xbcafea69,0xbd2fe007,0xbd3c6dd5,
  0x80000000,0xbc16cb58,0xbd96a905,0xbda973ba,0xbc96c9b6,0xbce22a7a,0xbdbc3ac3,0xbdcefdb7,0xbd16c32c,0xbd3c6dd5,0xbde1bc2e,0xbdf475c0,
  0xbd621469,0xbd83db0a,0xbe039502,0xbe0cec4a,0x80000000,0xbc7b514b,0xbdfab273,0xbe0cec4a,0xbcfb49ba,0xbd3c6dd5,0xbe1c76de,0xbe2bf804,
  0xbd7b2b74,0xbd9cecf9,0xbe3b6ecf,0xbe4ada4f,0xbdbc3ac3,0xbddb7d37,0xbe5a3997,0xbe698bba,0x80000000,0xbcafea69,0xbe2f10a2,0xbe44b0b9,
  0xbd2fe007,0xbd83db0a,0xbe5a3997,0xbe6fa8b2,0xbdafb680,0xbddb7d37,0xbe827dc0,0xbe8d17c0,0xbe039502,0xbe195be0,0xbe97a117,0xbea21887,
  0x80000000,0xbce22a7a,0xbe605c13,0xbe7bdba4,0xbd621469,0xbda973ba,0xbe8b9507,0xbe9920fe,0xbde1bc2e,0xbe0cec4a,0xbea68f12,0xbeb3dca5,
  0xbe28defc,0xbe44b0b9,0xbec1071e,0xbece0bea,0x80000000,0xbd0a342f,0xbe888e93,0xbe9920fe,0xbd8a200a,0xbdcefdb7,0xbea986c4,0xbeb9bb1e,
  0xbe09cf86,0xbe2bf804,0xbec9b953,0xbed97cb9,0xbe4dee60,0xbe6fa8b2,0xbee900b7,0xbef840c8,0x80000000,0xbd2351cb,0xbea09ae5,0xbeb3dca5,
  0xbda3308c,0xbdf475c0,0xbec6d529,0xbed97cb9,0xbe22abb6,0xbe4ada4f,0xbeebcbbb,0xbefdbabb,0xbe72b651,0xbe8d17c0,0xbf07a136,0xbf102dd5,
  0x80000000,0xbd3c6dd5,0xbeb8442a,0xbece0bea,0xbdbc3ac3,0xbe0cec4a,0xbee363fa,0xbef840c8,0xbe3b6ecf,0xbe698bba,0xbf064b82,0xbf102dd5,
  0xbe8b9507,0xbea21887,0xbf19c200,0xbf2302d3,0x80000000,0xbd55880e,0xbecf7bca,0xbee79a5d,0xbdd53db9,0xbe1f917b,0xbeff17b2,0xbf0af1b7,
  0xbe541501,0xbe840270,0xbf15f6d9,0xbf209393,0xbe9d9e78,0xbeb6ccc3,0xbf2ac082,0xbf34768f,0x80000000,0xbd6ea038,0xbee63375,0xbf003a06,
  0xbdee3876,0xbe3228d4,0xbf0cead0,0xbf19210f,0xbe6c9a7f,0xbe931f35,0xbf24d225,0xbf2ff3e6,0xbeaf713a,0xbecb2aae,0xbf3a7ca4,0xbf446337,
  0x80000000,0xbd83db0a,0xbefc5d27,0xbf0c42c9,0xbe039502,0xbe44b0b9,0xbf19c200,0xbf269de3,0xbe827dc0,0xbea21887,0xbf32c8c9,0xbf3e35c5,
  0xbec1071e,0xbedf28a9,0xbf48d8b3,0xbf52a649,0x80000000,0xbd9064b4,0xbf08f59b,0xbf17de12,0xbe1008b7,0xbe57278f,0xbf26050a,0xbf33587a,
  0xbe8e9a22,0xbeb0eacb,0xbf3fc767,0xbf4b41fa,0xbed25a09,0xbef2bd43,0xbf55b993,0xbf5f20db,0x80000000,0xbd9cecf9,0xbf13682a,0xbf2302d3,
  0xbe1c76de,0xbe698bba,0xbf31a81d,0xbf3f41fc,0xbe9aa086,0xbebf926f,0xbf4bbbf8,0xbf570348,0xbee363fa,0xbf02ef9f,0xbf6106f2,0xbf69b7e4,
  0x80000000,0xbda973ba,0xbf1d7fd1,0xbf2da859,0xbe28defc,0xbe7bdba4,0xbf3ca003,0xbf4a4c87,0xbea68f12,0xbece0bea,0xbf5695e5,0xbf61668a,
  0xbef41f07,0xbf0c42c9,0xbf6aab7b,0xbf725470,0x80000000,0xbdb5f8da,0xbf273656,0xbf37c655,0xbe354098,0xbe870ada,0xbf46e22a,0xbf546b3b,
  0xbeb263ef,0xbedc53c1,0xbf604621,0xbf6a5ad9,0xbf0242b1,0xbf1553b7,0xbf7294f8,0xbf78e3d6,0x80000000,0xbdc27c39,0xbf3085bb,0xbf4154e1,
  0xbe419b37,0xbe901c2c,0xbf5064af,0xbf5d924d,0xbebe1d4a,0xbeea6681,0xbf68bf3c,0xbf71d19f,0xbf0a48ad,0xbf1e1e22,0xbf78b47b,0xbf7d57de,
  0x80000000,0xbdcefdb7,0xbf396842,0xbf4a4c87,0xbe4dee60,0xbe9920fe,0xbf591e6a,0xbf65b710,0xbec9b953,0xbef840c8,0xbf6ff573,0xbf77beb7,
  0xbf121eb0,0xbf269de3,0xbf7cfe73,0xbf7fa6e3,0x80000000,0xbddb7d37,0xbf41d870,0xbf52a649,0xbe5a3997,0xbea21887,0xbf6106f2,0xbf6cd007,
  0xbed53641,0xbf02ef9f,0xbf75dec6,0xbf7c187a,0xbf19c200,0xbf2ecef7,0xbf7f6ac7,0xbf7fcbe2,0x80000000,0xbde7fa9a,0xbf49d112,0xbf5a5ba0,
  0xbe667c66,0xbeab0201,0xbf6816a8,0xbf72d4eb,0xbee0924f,0xbf099f4e,0xbf7a7302,0xbf7ed7d4,0xbf212ff9,0xbf36ad7f,0xbf7ff4e6,0xbf7dc68c,
  0x80000000,0xbdf475c0,0xbf514d3d,0xbf61668a,0xbe72b651,0xbeb3dca5,0xbf6e46be,0xbf77beb7,0xbeebcbbb,0xbf102dd5,0xbf7dabcc,0xbf7ff84a,
  0xbf286605,0xbf3e35c5,0xbf7e9bc9,0xbf799b43,0x80000000,0xbe007745,0xbf584853,0xbf67c187,0xbe7ee6e1,0xbebca7af,0xbf73913f,0xbf7b87b2,
  0xbef6e0cb,0xbf16999f,0xbf7f84ab,0xbf7f7808,0xbf2f61a5,0xbf456439,0xbf7b61fc,0xbf73530e,0x80000000,0xbe06b26e,0xbf5ebe05,0xbf6d67a1,
  0xbe8586ce,0xbec5625c,0xbf77f110,0xbf7e2b72,0xbf00e7e4,0xbf1ce11f,0xbf7ffb11,0xbf7d57de,0xbf36206c,0xbf4c3578,0xbf764d97,0xbf6afb8c,
  0x80000000,0xbe0cec4a,0xbf64aa59,0xbf725470,0xbe8b9507,0xbece0bea,0xbf7b61fc,0xbf7fa6e3,0xbf064b82,0xbf2302d3,0xbf7f0e58,0xbf799b43,
  0xbf3ca003,0xbf52a649,0xbf6f6830,0xbf60a6cf,0x80000000,0xbe1324ca,0xbf6a09a7,0xbf76841b,0xbe919ddd,0xbed6a399,0xbf7de0b1,0xbf7ff84a,
  0xbf0b9a6b,0xbf28fd41,0xbf7cbfc9,0xbf74484b,0xbf42de29,0xbf58b3a1,0xbf66becc,0xbf546b3b,0x80000000,0xbe195be0,0xbf6ed89e,0xbf79f35e,
  0xbe97a117,0xbedf28a9,0xbf7f6ac7,0xbf7f1f49,0xbf10d3cd,0xbf2ecef7,0xbf791298,0xbf6d67a1,0xbf48d8b3,0xbf5e5aa6,0xbf5c61c7,0xbf466354,
  0x80000000,0xbe1f917b,0xbf731447,0xbf7c9f8a,0xbe9d9e78,0xbee79a5d,0xbf7ffec4,0xbf7d1cdd,0xbf15f6d9,0xbf34768f,0xbf740bdd,0xbf650479,
  0xbf4e8d90,0xbf6398ac,0xbf5064af,0xbf36ad7f,0x80000000,0xbe25c58c,0xbf76ba07,0xbf7e868b,0xbea395c5,0xbeeff7fb,0xbf7f9c18,0xbf79f35e,
  0xbf1b02c6,0xbf39f2ac,0xbf6db293,0xbf5b2c79,0xbf53fac3,0xbf686b39,0xbf42de29,0xbf256bcb,0x80000000,0xbe2bf804,0xbf79c79d,0xbf7fa6e3,
  0xbea986c4,0xbef840c8,0xbf7e4323,0xbf75a67b,0xbf1ff6cb,0xbf3f41fc,0xbf660f88,0xbf4fefa8,0xbf591e6a,0xbf6cd007,0xbf33e7bc,0xbf12c39a,
  0x80000000,0xbe3228d4,0xbf7c3b28,0xbf7fffb1,0xbeaf713a,0xbf003a06,0xbf7bf531,0xbf703b37,0xbf24d225,0xbf446337,0xbf5d2d53,0xbf436051,
  0xbf5df6be,0xbf70c501,0xbf239da9,0xbefdbabb,0x80000000,0xbe3857ec,0xbf7e1324,0xbf7f90b1,0xbeb554ec,0xbf044889,0xbf78b47b,0xbf69b7e4,
  0xbf299415,0xbf495521,0xbf531849,0xbf3592e7,0xbf628210,0xbf74484b,0xbf121eb0,0xbed3c867,0x80000000,0xbe3e853e,0xbf7f4e6d,0xbf7e5a38,
  0xbebb31a0,0xbf084b92,0xbf748422,0xbf62241a,0xbf2e3bde,0xbf4e1689,0xbf47de65,0xbf269de3,0xbf66becc,0xbf77583a,0xbeff17b2,0xbea80b1f,
  0x80000000,0xbe44b0b9,0xbf7fec43,0xbf7c5d3a,0xbec1071e,0xbf0c42c9,0xbf6f6830,0xbf5988ad,0xbf32c8c9,0xbf52a649,0xbf3b8f3b,0xbf16999f,
  0xbf6aab7b,0xbf79f35e,0xbed8106b,0xbe75c35a,
};
__device__ __align__(128) const uint32_t c_img[1536] = {
  0x3f803f80,0x3f803f80,0x3f803f80,0x3f803f80,0x3f803f80,0x3f803f80,0x3f803f80,0x3f803f80,0x3f803f80,0x3f803f80,0x3f803f80,0x3f803f80,
  0x3f803f80,0x3f803f80,0x3f803f80,0x3f803f80,0x3f803f80,0x3f803f80,0x3f803f80,0x3f803f80,0x3f803f80,0x3f803f80,0x3f803f80,0x3f803f80,
  0x3f803f80,0x3f803f80,0x3f803f80,0x3f803f80,0x3f803f80,0x3f803f80,0x3f803f80,0x3f803f80,0x3f803f80,0x3f803f80,0x3f803f80,0x3f803f80,
  0x3f803f80,0x3f803f80,0x3f803f80,0x3f803f80,0x3f803f80,0x3f803f80,0x3f803f80,0x3f803f80,0x3f803f80,0x3f803f80,0x3f803f80,0x3f803f80,
  0x3f803f80,0x3f803f80,0x3f803f80,0x3f803f80,0x3f803f80,0x3f803f80,0x3f803f80,0x3f803f80,0x3f803f80,0x3f803f80,0x3f803f80,0x3f803f80,
  0x3f803f80,0x3f803f80,0x3f803f80,0x3f803f80,0x3f803f80,0x3f803f80,0x3f803f80,0x3f803f80,0x3f803f80,0x3f803f80,0x3f803f80,0x3f803f80,
  0x3f803f80,0x3f803f80,0x3f803f80,0x3f803f80,0x3f803f80,0x3f803f80,0x3f803f80,0x3f803f80,0x3f803f80,0x3f803f80,0x3f803f80,0x3f803f80,
  0x3f803f80,0x3f803f80,0x3f803f80,0x3f803f80,0x3f803f80,0x3f803f80,0x3f803f80,0x3f803f80,0x3f803f80,0x3f803f80,0x3f803f80,0x3f803f80,
  0x3f803f80,0x3f803f80,0x3f803f80,0x3f803f80,0x3f803f80,0x3f803f80,0x3f803f80,0x3f803f80,0x3f803f80,0x3f803f80,0x3f803f80,0x3f803f80,
  0x3f803f80,0x3f803f80,0x3f803f80,0x3f803f80,0x3f803f80,0x3f803f80,0x3f803f80,0x3f803f80,0x3f803f80,0x3f803f80,0x3f803f80,0x3f803f80,
  0x3f803f80,0x3f803f80,0x3f803f80,0x3f803f80,0x3f803f80,0x3f803f80,0x3f803f80,0x3f803f80,0x3f803f80,0x3f803f80,0x3f803f80,0x3f803f80,
  0x3f803f80,0x3f803f80,0x3f803f80,0x3f803f80,0x3f803f80,0x3f803f80,0x3f803f80,0x3f803f80,0x3f803f80,0x3f803f80,0x3f803f80,0x3f803f80,
  0x3f803f80,0x3f803f80,0x3f803f80,0x3f803f80,0x3f803f80,0x3f803f80,0x3f803f80,0x3f803f80,0x3f803f80,0x3f803f80,0x3f803f80,0x3f803f80,
  0x3f803f80,0x3f803f80,0x3f803f80,0x3f803f80,0x3f803f80,0x3f803f80,0x3f803f80,0x3f803f80,0x3f803f80,0x3f803f80,0x3f803f80,0x3f803f80,
  0x3f803f80,0x3f803f80,0x3f803f80,0x3f803f80,0x3f803f80,0x3f803f80,0x3f803f80,0x3f803f80,0x3f803f80,0x3f803f80,0x3f803f80,0x3f803f80,
  0x3f803f80,0x3f803f80,0x3f803f80,0x3f803f80,0x3f803f80,0x3f803f80,0x3f803f80,0x3f803f80,0x3f803f80,0x3f803f80,0x3f803f80,0x3f803f80,
  0x3f803f80,0x3f803f80,0x3f803f80,0x3f803f80,0x3f803f80,0x3f803f80,0x3f803f80,0x3f803f80,0x3f803f80,0x3f803f80,0x3f803f80,0x3f803f80,
  0x3f803f80,0x3f803f80,0x3f803f80,0x3f803f80,0x3f803f80,0x3f803f80,0x3f803f80,0x3f803f80,0x3f803f80,0x3f803f80,0x3f803f80,0x3f803f80,
  0x3f803f80,0x3f803f80,0x3f803f80,0x3f803f80,0x3f803f80,0x3f803f80,0x3f803f80,0x3f803f80,0x3f803f80,0x3f803f80,0x3f803f80,0x3f803f80,
  0x3f803f80,0x3f803f80,0x3f803f80,0x3f803f80,0x3f803f80,0x3f803f80,0x3f803f80,0x3f803f80,0x3f803f80,0x3f803f80,0x3f803f80,0x3f803f80,
  0x3f803f80,0x3f803f80,0x3f803f80,0x3f803f80,0x3f803f80,0x3f803f80,0x3f803f80,0x3f803f80,0x3f803f80,0x3f803f80,0x3f803f80,0x3f803f80,
  0x3f803f80,0x3f803f80,0x3f803f80,0x3f803f80,0x3f803f80,0x3f803f80,0x3f803f80,0x3f803f80,0x3f803f80,0x3f803f80,0x3f803f80,0x3f803f80,
  0x3f803f80,0x3f803f80,0x3f803f80,0x3f803f80,0x3f803f80,0x3f803f80,0x3f803f80,0x3f803f80,0x3f803f80,0x3f803f80,0x3f803f80,0x3f803f80,
  0x3f803f80,0x3f803f80,0x3f803f80,0x3f803f80,0x3f803f80,0x3f803f80,0x3f803f80,0x3f803f80,0x3f803f80,0x3f803f80,0x3f803f80,0x3f803f80,
  0x3f803f80,0x3f803f80,0x3f803f80,0x3f803f80,0x3f803f80,0x3f803f80,0x3f803f80,0x3f803f80,0x3f803f80,0x3f803f80,0x3f803f80,0x3f803f80,
  0x3f803f80,0x3f803f80,0x3f803f80,0x3f803f80,0x3f803f80,0x3f803f80,0x3f803f80,0x3f803f80,0x3f803f80,0x3f803f80,0x3f803f80,0x3f803f80,
  0x3f803f80,0x3f803f80,0x3f803f80,0x3f803f80,0x3f803f80,0x3f803f80,0x3f803f80,0x3f803f80,0x3f803f80,0x3f803f80,0x3f803f80,0x3f803f80,
  0x3f803f80,0x3f803f80,0x3f803f80,0x3f803f80,0x3f803f80,0x3f803f80,0x3f803f80,0x3f803f80,0x3f803f80,0x3f803f80,0x3f803f80,0x3f803f80,
  0x3f803f80,0x3f803f80,0x3f803f80,0x3f803f80,0x3f803f80,0x3f803f80,0x3f803f80,0x3f803f80,0x3f803f80,0x3f803f80,0x3f803f80,0x3f803f80,
  0x3f803f80,0x3f803f80,0x3f803f80,0x3f803f80,0x3f803f80,0x3f803f80,0x3f803f80,0x3f803f80,0x3f803f80,0x3f803f80,0x3f803f80,0x3f803f80,
  0x3f803f80,0x3f803f80,0x3f803f80,0x3f803f80,0x3f803f80,0x3f803f80,0x3f803f80,0x3f803f80,0x3f803f80,0x3f803f80,0x3f803f80,0x3f803f80,
  0x3f803f80,0x3f803f80,0x3f803f80,0x3f803f80,0x3f803f80,0x3f803f80,0x3f803f80,0x3f803f80,0x3f803f80,0x3f803f80,0x3f803f80,0x3f803f80,
  0x3f803f80,0x3f803f80,0x3f803f80,0x3f803f80,0x3f803f80,0x3f803f80,0x3f803f80,0x3f803f80,0x3f803f80,0x3f803f80,0x3f803f80,0x3f803f80,
  0x3f803f80,0x3f803f80,0x3f803f80,0x3f803f80,0x3f803f80,0x3f803f80,0x3f803f80,0x3f803f80,0x3f803f80,0x3f803f80,0x3f803f80,0x3f803f80,
  0x3f803f80,0x3f803f80,0x3f803f80,0x3f803f80,0x3f803f80,0x3f803f80,0x3f803f80,0x3f803f80,0x3f803f80,0x3f803f80,0x3f803f80,0x3f803f80,
  0x3f803f80,0x3f803f80,0x3f803f80,0x3f803f80,0x3f803f80,0x3f803f80,0x3f803f80,0x3f803f80,0x3f803f80,0x3f803f80,0x3f803f80,0x3f803f80,
  0x3f803f80,0x3f803f80,0x3f803f80,0x3f803f80,0x3f803f80,0x3f803f80,0x3f803f80,0x3f803f80,0x3f803f80,0x3f803f80,0x3f803f80,0x3f803f80,
  0x3f803f80,0x3f803f80,0x3f803f80,0x3f803f80,0x3f803f80,0x3f803f80,0x3f803f80,0x3f803f80,0x3f803f80,0x3f803f80,0x3f803f80,0x3f803f80,
  0x3f803f80,0x3f803f80,0x3f803f80,0x3f803f80,0x3f803f80,0x3f803f80,0x3f803f80,0x3f803f80,0x3f803f80,0x3f803f80,0x3f803f80,0x3f803f80,
  0x3f803f80,0x3f803f80,0x3f803f80,0x3f803f80,0x3f803f80,0x3f803f80,0x3f803f80,0x3f803f80,0x3f803f80,0x3f803f80,0x3f803f80,0x3f803f80,
  0x3f803f80,0x3f803f80,0x3f803f80,0x3f803f80,0x3f803f80,0x3f803f80,0x3f803f80,0x3f803f80,0x3f803f80,0x3f803f80,0x3f803f80,0x3f803f80,
  0x3f803f80,0x3f803f80,0x3f803f80,0x3f803f80,0x3f803f80,0x3f803f80,0x3f803f80,0x3f803f80,0x3f803f80,0x3f803f80,0x3f803f80,0x3f803f80,
  0x3f803f80,0x3f803f80,0x3f803f80,0x3f803f80,0x3f803f80,0x3f803f80,0x3f803f80,0x3f803f80,0x3f803f80,0x3f803f80,0x3f803f80,0x3f803f80,
  0x3f6d3f80,0x3ec43f35,0xbec40000,0xbf6dbf35,0x3f353f80,0xbf350000,0xbf35bf80,0x3f350000,0x3ec43f80,0xbf6dbf35,0x3f6d0000,0xbec43f35,
  0x00003f80,0x0000bf80,0x00003f80,0x0000bf80,0xbec43f80,0x3f6dbf35,0xbf6d0000,0x3ec43f35,0xbf353f80,0x3f350000,0x3f35bf80,0xbf350000,
  0xbf6d3f80,0xbec43f35,0x3ec40000,0x3f6dbf35,0x3f803f80,0x3f803f80,0x3f803f80,0x3f803f80,0xbf6dbf80,0xbec4bf35,0x3ec40000,0x3f6d3f35,
  0x3f353f80,0xbf350000,0xbf35bf80,0x3f350000,0xbec4bf80,0x3f6d3f35,0xbf6d0000,0x3ec4bf35,0x00003f80,0x0000bf80,0x00003f80,0x0000bf80,
  0x3ec4bf80,0xbf6d3f35,0x3f6d0000,0xbec4bf35,0xbf353f80,0x3f350000,0x3f35bf80,0xbf350000,0x3f6dbf80,0x3ec4bf35,0xbec40000,0xbf6d3f35,
  0x00000000,0x00000000,0x00000000,0x00000000,0x3ec40000,0x3f6d3f35,0x3f6d3f80,0x3ec43f35,0x3f350000,0x3f353f80,0xbf350000,0xbf35bf80,
  0x3f6d0000,0xbec43f35,0xbec4bf80,0x3f6d3f35,0x3f800000,0xbf800000,0x3f800000,0xbf800000,0x3f6d0000,0xbec4bf35,0xbec43f80,0x3f6dbf35,
  0x3f350000,0x3f35bf80,0xbf350000,0xbf353f80,0x3ec40000,0x3f6dbf35,0x3f6dbf80,0x3ec4bf35,0x00000000,0x00000000,0x00000000,0x00000000,
  0xbec40000,0xbf6dbf35,0xbf6dbf80,0xbec4bf35,0x3f350000,0x3f353f80,0xbf350000,0xbf35bf80,0xbf6d0000,0x3ec4bf35,0x3ec43f80,0xbf6dbf35,
  0x3f800000,0xbf800000,0x3f800000,0xbf800000,0xbf6d0000,0x3ec43f35,0x3ec4bf80,0xbf6d3f35,0x3f350000,0x3f35bf80,0xbf350000,0xbf353f80,
  0xbec40000,0xbf6d3f35,0xbf6d3f80,0xbec43f35,0xbf803f80,0xbf803f80,0xbf803f80,0xbf803f80,0xbf6d3f80,0xbec43f35,0x3ec40000,0x3f6dbf35,
  0xbf353f80,0x3f350000,0x3f35bf80,0xbf350000,0xbec43f80,0x3f6dbf35,0xbf6d0000,0x3ec43f35,0x00003f80,0x0000bf80,0x00003f80,0x0000bf80,
  0x3ec43f80,0xbf6dbf35,0x3f6d0000,0xbec43f35,0x3f353f80,0xbf350000,0xbf35bf80,0x3f350000,0x3f6d3f80,0x3ec43f35,0xbec40000,0xbf6dbf35,
  0xbf803f80,0xbf803f80,0xbf803f80,0xbf803f80,0x3f6dbf80,0x3ec4bf35,0xbec40000,0xbf6d3f35,0xbf353f80,0x3f350000,0x3f35bf80,0xbf350000,
  0x3ec4bf80,0xbf6d3f35,0x3f6d0000,0xbec4bf35,0x00003f80,0x0000bf80,0x00003f80,0x0000bf80,0xbec4bf80,0x3f6d3f35,0xbf6d0000,0x3ec4bf35,
  0x3f353f80,0xbf350000,0xbf35bf80,0x3f350000,0xbf6dbf80,0xbec4bf35,0x3ec40000,0x3f6d3f35,0x00000000,0x00000000,0x00000000,0x00000000,
  0xbec40000,0xbf6d3f35,0xbf6d3f80,0xbec43f35,0xbf350000,0xbf353f80,0x3f350000,0x3f35bf80,0xbf6d0000,0x3ec43f35,0x3ec4bf80,0xbf6d3f35,
  0xbf800000,0x3f800000,0xbf800000,0x3f800000,0xbf6d0000,0x3ec4bf35,0x3ec43f80,0xbf6dbf35,0xbf350000,0xbf35bf80,0x3f350000,0x3f353f80,
  0xbec40000,0xbf6dbf35,0xbf6dbf80,0xbec4bf35,0x00000000,0x00000000,0x00000000,0x00000000,0x3ec40000,0x3f6dbf35,0x3f6dbf80,0x3ec4bf35,
  0xbf350000,0xbf353f80,0x3f350000,0x3f35bf80,0x3f6d0000,0xbec4bf35,0xbec43f80,0x3f6dbf35,0xbf800000,0x3f800000,0xbf800000,0x3f800000,
  0x3f6d0000,0xbec43f35,0xbec4bf80,0x3f6d3f35,0xbf350000,0xbf35bf80,0x3f350000,0x3f353f80,0x3ec40000,0x3f6d3f35,0x3f6d3f80,0x3ec43f35,
  0x80008000,0x80008000,0x80008000,0x80008000,0xbec48000,0xbf6dbf35,0xbf6dbf80,0xbec4bf35,0xbf358000,0xbf35bf80,0x3f358000,0x3f353f80,
  0xbf6d8000,0x3ec4bf35,0x3ec43f80,0xbf6dbf35,0xbf808000,0x3f808000,0xbf808000,0x3f808000,0xbf6d8000,0x3ec43f35,0x3ec4bf80,0xbf6d3f35,
  0xbf358000,0xbf353f80,0x3f358000,0x3f35bf80,0xbec48000,0xbf6d3f35,0xbf6d3f80,0xbec43f35,0x80008000,0x80008000,0x80008000,0x80008000,
  0x3ec48000,0x3f6d3f35,0x3f6d3f80,0x3ec43f35,0xbf358000,0xbf35bf80,0x3f358000,0x3f353f80,0x3f6d8000,0xbec43f35,0xbec4bf80,0x3f6d3f35,
  0xbf808000,0x3f808000,0xbf808000,0x3f808000,0x3f6d8000,0xbec4bf35,0xbec43f80,0x3f6dbf35,0xbf358000,0xbf353f80,0x3f358000,0x3f35bf80,
  0x3ec48000,0x3f6dbf35,0x3f6dbf80,0x3ec4bf35,0x3f803f80,0x3f803f80,0x3f803f80,0x3f803f80,0x3f6d3f80,0x3ec43f35,0xbec40000,0xbf6dbf35,
  0x3f353f80,0xbf350000,0xbf35bf80,0x3f350000,0x3ec43f80,0xbf6dbf35,0x3f6d0000,0xbec43f35,0x00003f80,0x0000bf80,0x00003f80,0x0000bf80,
  0xbec43f80,0x3f6dbf35,0xbf6d0000,0x3ec43f35,0xbf353f80,0x3f350000,0x3f35bf80,0xbf350000,0xbf6d3f80,0xbec43f35,0x3ec40000,0x3f6dbf35,
  0x3f803f80,0x3f803f80,0x3f803f80,0x3f803f80,0xbf6dbf80,0xbec4bf35,0x3ec40000,0x3f6d3f35,0x3f353f80,0xbf350000,0xbf35bf80,0x3f350000,
  0xbec4bf80,0x3f6d3f35,0xbf6d0000,0x3ec4bf35,0x00003f80,0x0000bf80,0x00003f80,0x0000bf80,0x3ec4bf80,0xbf6d3f35,0x3f6d0000,0xbec4bf35,
  0xbf353f80,0x3f350000,0x3f35bf80,0xbf350000,0x3f6dbf80,0x3ec4bf35,0xbec40000,0xbf6d3f35,0x80008000,0x80008000,0x80008000,0x80008000,
  0x3ec48000,0x3f6dbf35,0x3f6dbf80,0x3ec4bf35,0x3f358000,0x3f35bf80,0xbf358000,0xbf353f80,0x3f6d8000,0xbec4bf35,0xbec43f80,0x3f6dbf35,
  0x3f808000,0xbf808000,0x3f808000,0xbf808000,0x3f6d8000,0xbec43f35,0xbec4bf80,0x3f6d3f35,0x3f358000,0x3f353f80,0xbf358000,0xbf35bf80,
  0x3ec48000,0x3f6d3f35,0x3f6d3f80,0x3ec43f35,0x80008000,0x80008000,0x80008000,0x80008000,0xbec48000,0xbf6d3f35,0xbf6d3f80,0xbec43f35,
  0x3f358000,0x3f35bf80,0xbf358000,0xbf353f80,0xbf6d8000,0x3ec43f35,0x3ec4bf80,0xbf6d3f35,0x3f808000,0xbf808000,0x3f808000,0xbf808000,
  0xbf6d8000,0x3ec4bf35,0x3ec43f80,0xbf6dbf35,0x3f358000,0x3f353f80,0xbf358000,0xbf35bf80,0xbec48000,0xbf6dbf35,0xbf6dbf80,0xbec4bf35,
  0xbf803f80,0xbf803f80,0xbf803f80,0xbf803f80,0xbf6d3f80,0xbec43f35,0x3ec40000,0x3f6dbf35,0xbf353f80,0x3f350000,0x3f35bf80,0xbf350000,
  0xbec43f80,0x3f6dbf35,0xbf6d0000,0x3ec43f35,0x00003f80,0x0000bf80,0x00003f80,0x0000bf80,0x3ec43f80,0xbf6dbf35,0x3f6d0000,0xbec43f35,
  0x3f353f80,0xbf350000,0xbf35bf80,0x3f350000,0x3f6d3f80,0x3ec43f35,0xbec40000,0xbf6dbf35,0xbf803f80,0xbf803f80,0xbf803f80,0xbf803f80,
  0x3f6dbf80,0x3ec4bf35,0xbec40000,0xbf6d3f35,0xbf353f80,0x3f350000,0x3f35bf80,0xbf350000,0x3ec4bf80,0xbf6d3f35,0x3f6d0000,0xbec4bf35,
  0x00003f80,0x0000bf80,0x00003f80,0x0000bf80,0xbec4bf80,0x3f6d3f35,0xbf6d0000,0x3ec4bf35,0x3f353f80,0xbf350000,0xbf35bf80,0x3f350000,
  0xbf6dbf80,0xbec4bf35,0x3ec40000,0x3f6d3f35,0x3f803f80,0x3f803f80,0x3f803f80,0x3f803f80,0x3f6d3f80,0x3ec43f35,0xbec40000,0xbf6dbf35,
  0x3f353f80,0xbf350000,0xbf35bf80,0x3f350000,0x3ec43f80,0xbf6dbf35,0x3f6d0000,0xbec43f35,0x00003f80,0x0000bf80,0x00003f80,0x0000bf80,
  0xbec43f80,0x3f6dbf35,0xbf6d0000,0x3ec43f35,0xbf353f80,0x3f350000,0x3f35bf80,0xbf350000,0xbf6d3f80,0xbec43f35,0x3ec40000,0x3f6dbf35,
  0x3f803f80,0x3f803f80,0x3f803f80,0x3f803f80,0xbf6dbf80,0xbec4bf35,0x3ec40000,0x3f6d3f35,0x3f353f80,0xbf350000,0xbf35bf80,0x3f350000,
  0xbec4bf80,0x3f6d3f35,0xbf6d0000,0x3ec4bf35,0x00003f80,0x0000bf80,0x00003f80,0x0000bf80,0x3ec4bf80,0xbf6d3f35,0x3f6d0000,0xbec4bf35,
  0xbf353f80,0x3f350000,0x3f35bf80,0xbf350000,0x3f6dbf80,0x3ec4bf35,0xbec40000,0xbf6d3f35,0x80008000,0x80008000,0x80008000,0x80008000,
  0xbec48000,0xbf6dbf35,0xbf6dbf80,0xbec4bf35,0xbf358000,0xbf35bf80,0x3f358000,0x3f353f80,0xbf6d8000,0x3ec4bf35,0x3ec43f80,0xbf6dbf35,
  0xbf808000,0x3f808000,0xbf808000,0x3f808000,0xbf6d8000,0x3ec43f35,0x3ec4bf80,0xbf6d3f35,0xbf358000,0xbf353f80,0x3f358000,0x3f35bf80,
  0xbec48000,0xbf6d3f35,0xbf6d3f80,0xbec43f35,0x80008000,0x80008000,0x80008000,0x80008000,0x3ec48000,0x3f6d3f35,0x3f6d3f80,0x3ec43f35,
  0xbf358000,0xbf35bf80,0x3f358000,0x3f353f80,0x3f6d8000,0xbec43f35,0xbec4bf80,0x3f6d3f35,0xbf808000,0x3f808000,0xbf808000,0x3f808000,
  0x3f6d8000,0xbec4bf35,0xbec43f80,0x3f6dbf35,0xbf358000,0xbf353f80,0x3f358000,0x3f35bf80,0x3ec48000,0x3f6dbf35,0x3f6dbf80,0x3ec4bf35,
  0xbf803f80,0xbf803f80,0xbf803f80,0xbf803f80,0xbf6d3f80,0xbec43f35,0x3ec40000,0x3f6dbf35,0xbf353f80,0x3f350000,0x3f35bf80,0xbf350000,
  0xbec43f80,0x3f6dbf35,0xbf6d0000,0x3ec43f35,0x00003f80,0x0000bf80,0x00003f80,0x0000bf80,0x3ec43f80,0xbf6dbf35,0x3f6d0000,0xbec43f35,
  0x3f353f80,0xbf350000,0xbf35bf80,0x3f350000,0x3f6d3f80,0x3ec43f35,0xbec40000,0xbf6dbf35,0xbf803f80,0xbf803f80,0xbf803f80,0xbf803f80,
  0x3f6dbf80,0x3ec4bf35,0xbec40000,0xbf6d3f35,0xbf353f80,0x3f350000,0x3f35bf80,0xbf350000,0x3ec4bf80,0xbf6d3f35,0x3f6d0000,0xbec4bf35,
  0x00003f80,0x0000bf80,0x00003f80,0x0000bf80,0xbec4bf80,0x3f6d3f35,0xbf6d0000,0x3ec4bf35,0x3f353f80,0xbf350000,0xbf35bf80,0x3f350000,
  0xbf6dbf80,0xbec4bf35,0x3ec40000,0x3f6d3f35,0x80008000,0x80008000,0x80008000,0x80008000,0x3ec48000,0x3f6dbf35,0x3f6dbf80,0x3ec4bf35,
  0x3f358000,0x3f35bf80,0xbf358000,0xbf353f80,0x3f6d8000,0xbec4bf35,0xbec43f80,0x3f6dbf35,0x3f808000,0xbf808000,0x3f808000,0xbf808000,
  0x3f6d8000,0xbec43f35,0xbec4bf80,0x3f6d3f35,0x3f358000,0x3f353f80,0xbf358000,0xbf35bf80,0x3ec48000,0x3f6d3f35,0x3f6d3f80,0x3ec43f35,
  0x80008000,0x80008000,0x80008000,0x80008000,0xbec48000,0xbf6d3f35,0xbf6d3f80,0xbec43f35,0x3f358000,0x3f35bf80,0xbf358000,0xbf353f80,
  0xbf6d8000,0x3ec43f35,0x3ec4bf80,0xbf6d3f35,0x3f808000,0xbf808000,0x3f808000,0xbf808000,0xbf6d8000,0x3ec4bf35,0x3ec43f80,0xbf6dbf35,
  0x3f358000,0x3f353f80,0xbf358000,0xbf35bf80,0xbec48000,0xbf6dbf35,0xbf6dbf80,0xbec4bf35,0x00000000,0x00000000,0x00000000,0x00000000,
  0x3ec40000,0x3f6d3f35,0x3f6d3f80,0x3ec43f35,0x3f350000,0x3f353f80,0xbf350000,0xbf35bf80,0x3f6d0000,0xbec43f35,0xbec4bf80,0x3f6d3f35,
  0x3f800000,0xbf800000,0x3f800000,0xbf800000,0x3f6d0000,0xbec4bf35,0xbec43f80,0x3f6dbf35,0x3f350000,0x3f35bf80,0xbf350000,0xbf353f80,
  0x3ec40000,0x3f6dbf35,0x3f6dbf80,0x3ec4bf35,0x00000000,0x00000000,0x00000000,0x00000000,0xbec40000,0xbf6dbf35,0xbf6dbf80,0xbec4bf35,
  0x3f350000,0x3f353f80,0xbf350000,0xbf35bf80,0xbf6d0000,0x3ec4bf35,0x3ec43f80,0xbf6dbf35,0x3f800000,0xbf800000,0x3f800000,0xbf800000,
  0xbf6d0000,0x3ec43f35,0x3ec4bf80,0xbf6d3f35,0x3f350000,0x3f35bf80,0xbf350000,0xbf353f80,0xbec40000,0xbf6d3f35,0xbf6d3f80,0xbec43f35,
  0x3f803f80,0x3f803f80,0x3f803f80,0x3f803f80,0x3f6d3f80,0x3ec43f35,0xbec40000,0xbf6dbf35,0x3f353f80,0xbf350000,0xbf35bf80,0x3f350000,
  0x3ec43f80,0xbf6dbf35,0x3f6d0000,0xbec43f35,0x00003f80,0x0000bf80,0x00003f80,0x0000bf80,0xbec43f80,0x3f6dbf35,0xbf6d0000,0x3ec43f35,
  0xbf353f80,0x3f350000,0x3f35bf80,0xbf350000,0xbf6d3f80,0xbec43f35,0x3ec40000,0x3f6dbf35,0x3f803f80,0x3f803f80,0x3f803f80,0x3f803f80,
  0xbf6dbf80,0xbec4bf35,0x3ec40000,0x3f6d3f35,0x3f353f80,0xbf350000,0xbf35bf80,0x3f350000,0xbec4bf80,0x3f6d3f35,0xbf6d0000,0x3ec4bf35,
  0x00003f80,0x0000bf80,0x00003f80,0x0000bf80,0x3ec4bf80,0xbf6d3f35,0x3f6d0000,0xbec4bf35,0xbf353f80,0x3f350000,0x3f35bf80,0xbf350000,
  0x3f6dbf80,0x3ec4bf35,0xbec40000,0xbf6d3f35,0x00000000,0x00000000,0x00000000,0x00000000,0xbec40000,0xbf6d3f35,0xbf6d3f80,0xbec43f35,
  0xbf350000,0xbf353f80,0x3f350000,0x3f35bf80,0xbf6d0000,0x3ec43f35,0x3ec4bf80,0xbf6d3f35,0xbf800000,0x3f800000,0xbf800000,0x3f800000,
  0xbf6d0000,0x3ec4bf35,0x3ec43f80,0xbf6dbf35,0xbf350000,0xbf35bf80,0x3f350000,0x3f353f80,0xbec40000,0xbf6dbf35,0xbf6dbf80,0xbec4bf35,
  0x00000000,0x00000000,0x00000000,0x00000000,0x3ec40000,0x3f6dbf35,0x3f6dbf80,0x3ec4bf35,0xbf350000,0xbf353f80,0x3f350000,0x3f35bf80,
  0x3f6d0000,0xbec4bf35,0xbec43f80,0x3f6dbf35,0xbf800000,0x3f800000,0xbf800000,0x3f800000,0x3f6d0000,0xbec43f35,0xbec4bf80,0x3f6d3f35,
  0xbf350000,0xbf35bf80,0x3f350000,0x3f353f80,0x3ec40000,0x3f6d3f35,0x3f6d3f80,0x3ec43f35,0xbf803f80,0xbf803f80,0xbf803f80,0xbf803f80,
  0xbf6d3f80,0xbec43f35,0x3ec40000,0x3f6dbf35,0xbf353f80,0x3f350000,0x3f35bf80,0xbf350000,0xbec43f80,0x3f6dbf35,0xbf6d0000,0x3ec43f35,
  0x00003f80,0x0000bf80,0x00003f80,0x0000bf80,0x3ec43f80,0xbf6dbf35,0x3f6d0000,0xbec43f35,0x3f353f80,0xbf350000,0xbf35bf80,0x3f350000,
  0x3f6d3f80,0x3ec43f35,0xbec40000,0xbf6dbf35,0xbf803f80,0xbf803f80,0xbf803f80,0xbf803f80,0x3f6dbf80,0x3ec4bf35,0xbec40000,0xbf6d3f35,
  0xbf353f80,0x3f350000,0x3f35bf80,0xbf350000,0x3ec4bf80,0xbf6d3f35,0x3f6d0000,0xbec4bf35,0x00003f80,0x0000bf80,0x00003f80,0x0000bf80,
  0xbec4bf80,0x3f6d3f35,0xbf6d0000,0x3ec4bf35,0x3f353f80,0xbf350000,0xbf35bf80,0x3f350000,0xbf6dbf80,0xbec4bf35,0x3ec40000,0x3f6d3f35,
};

__device__ __align__(128) float    g_kv[2][16][2176];
__device__ __align__(128) uint4    g_o[16 * 16 * 1024];
__device__ __align__(128) unsigned g_kvcnt[16 * 32];
__device__ __align__(128) unsigned g_ocnt[16 * 32];
__device__ unsigned g_epoch[128];
#define STAMP(role, i) do {} while (0)

constexpr int STAGE_BYTES = 57344;
constexpr int OFF_PK = 0, OFF_V = 114688, OFF_H = 4 * 16384, OFF_VP = 9 * 16384;
constexpr int OFF_XT = 172032, XT_STRIDE = 4112;
constexpr int OFF_ONES = 205824, OFF_F2F = 207872, OFF_F2I = 209920, OFF_KVB = 211968;
constexpr int OFF_STG = 217088, STG_STRIDE = 4224, OFF_BAR = 229760, SMEM_TOTAL = 230400;
enum { B_FULL1 = 0, B_EMPTY1 = 3, B_H = 6, B_XT = 8, B_KV = 9, B_Y = 10, B_PKFREE = 11, B_HFREE = 12, B_VFREE = 14,
       B_STG = 15, B_ODONE = 21, B_FULL2 = 24, B_CONS2 = 40, B_COUNT = 56 };
constexpr uint64_t SLOT_A = 0x5649256492564954ull;
constexpr uint64_t SLOT_B = 0x7103871038710326ull;
constexpr int SPIN_LIMIT = 1 << 22;

__device__ __forceinline__ uint32_t smem_u32(const void* p) { return (uint32_t)__cvta_generic_to_shared(p); }
__device__ __forceinline__ void wg_fence() { asm volatile("wgmma.fence.sync.aligned;" ::: "memory"); }
__device__ __forceinline__ void wg_commit() { asm volatile("wgmma.commit_group.sync.aligned;" ::: "memory"); }
template <int N> __device__ __forceinline__ void wg_wait() { asm volatile("wgmma.wait_group.sync.aligned %0;" ::"n"(N) : "memory"); }
template <int N> __device__ __forceinline__ void keep(float (&d)[N]) {
#pragma unroll
  for (int i = 0; i < N; i++) asm volatile("" : "+f"(d[i])::"memory");
}
__device__ __forceinline__ uint64_t mkdesc(uint32_t addr, uint32_t lbo, uint32_t sbo, uint32_t swz) {
  uint32_t lo = ((addr & 0x3FFFF) >> 4) | ((lbo >> 4) << 16), hi = (sbo >> 4) | (swz << 30);
  return ((uint64_t)hi << 32) | lo;
}
__device__ __forceinline__ void mbar_init(uint32_t bar, int cnt) { asm volatile("mbarrier.init.shared::cta.b64 [%0], %1;" ::"r"(bar), "r"(cnt)); }
__device__ __forceinline__ void mbar_expect(uint32_t bar, int bytes) { asm volatile("mbarrier.arrive.expect_tx.shared::cta.b64 _, [%0], %1;" ::"r"(bar), "r"(bytes) : "memory"); }
__device__ __forceinline__ void mbar_arrive(uint32_t bar) { asm volatile("mbarrier.arrive.shared::cta.b64 _, [%0];" ::"r"(bar) : "memory"); }
__device__ __forceinline__ void mbar_arrive_cl(uint32_t bar, uint32_t cta) {
  asm volatile("{\n.reg .b32 r;\nmapa.shared::cluster.u32 r, %0, %1;\nmbarrier.arrive.shared::cluster.b64 _, [r];\n}\n" ::"r"(bar), "r"(cta) : "memory");
}
__device__ __forceinline__ void mbar_wait(uint32_t bar, uint32_t parity) {
  asm volatile("{\n.reg .pred p;\n.reg .u32 n;\nmov.u32 n, 0;\n"
               "W_%=:\nmbarrier.try_wait.parity.shared::cta.b64 p, [%0], %1;\n@p bra D_%=;\n"
               "add.u32 n, n, 1;\nsetp.lt.u32 p, n, %2;\n@p bra W_%=;\ntrap;\nD_%=:\n}\n" ::"r"(bar), "r"(parity), "n"(SPIN_LIMIT) : "memory");
}
__device__ __forceinline__ void fence_async() { asm volatile("fence.proxy.async.shared::cta;" ::: "memory"); }
__device__ __forceinline__ void bar_sync(int id) { asm volatile("bar.sync %0, 128;" ::"r"(id) : "memory"); }
__device__ __forceinline__ void tma2d(uint32_t dst, const CUtensorMap* m, int c0, int c1, uint32_t bar) {
  asm volatile("cp.async.bulk.tensor.2d.shared::cluster.global.mbarrier::complete_tx::bytes [%0], [%1, {%3, %4}], [%2];"
               ::"r"(dst), "l"(m), "r"(bar), "r"(c0), "r"(c1) : "memory");
}
__device__ __forceinline__ void tma2d_mc(uint32_t dst, const CUtensorMap* m, int c0, int c1, uint32_t bar) {
  asm volatile("cp.async.bulk.tensor.2d.shared::cluster.global.mbarrier::complete_tx::bytes.multicast::cluster [%0], [%1, {%3, %4}], [%2], %5;"
               ::"r"(dst), "l"(m), "r"(bar), "r"(c0), "r"(c1), "h"((uint16_t)3) : "memory");
}
__device__ __forceinline__ void tma3d(uint32_t dst, const CUtensorMap* m, int c0, int c1, int c2, uint32_t bar) {
  asm volatile("cp.async.bulk.tensor.3d.shared::cluster.global.mbarrier::complete_tx::bytes [%0], [%1, {%3, %4, %5}], [%2];"
               ::"r"(dst), "l"(m), "r"(bar), "r"(c0), "r"(c1), "r"(c2) : "memory");
}
__device__ __forceinline__ void bulk_ld(uint32_t dst, const void* src, int bytes, uint32_t bar) {
  asm volatile("cp.async.bulk.shared::cluster.global.mbarrier::complete_tx::bytes [%0], [%1], %2, [%3];" ::"r"(dst), "l"(src), "r"(bytes), "r"(bar) : "memory");
}
__device__ __forceinline__ void bulk_ld_mc(uint32_t dst, const void* src, int bytes, uint32_t bar) {
  asm volatile("cp.async.bulk.shared::cluster.global.mbarrier::complete_tx::bytes.multicast::cluster [%0], [%1], %2, [%3], %4;"
               ::"r"(dst), "l"(src), "r"(bytes), "r"(bar), "h"((uint16_t)3) : "memory");
}
__device__ __forceinline__ void tma2d_st(const CUtensorMap* m, uint32_t src, int c0, int c1) {
  asm volatile("cp.async.bulk.tensor.2d.global.shared::cta.bulk_group [%0, {%2, %3}], [%1];" ::"l"(m), "r"(src), "r"(c0), "r"(c1) : "memory");
}
__device__ __forceinline__ void pf_l2(const void* p, int bytes) { asm volatile("cp.async.bulk.prefetch.L2.global [%0], %1;" ::"l"(p), "r"(bytes) : "memory"); }
__device__ __forceinline__ void pf_t2d(const CUtensorMap* m, int c0, int c1) {
  asm volatile("cp.async.bulk.prefetch.tensor.2d.L2.global [%0, {%1, %2}];" ::"l"(m), "r"(c0), "r"(c1) : "memory");
}
__device__ __forceinline__ void pf_t3d(const CUtensorMap* m, int c0, int c1, int c2) {
  asm volatile("cp.async.bulk.prefetch.tensor.3d.L2.global [%0, {%1, %2, %3}];" ::"l"(m), "r"(c0), "r"(c1), "r"(c2) : "memory");
}
__device__ __forceinline__ void ldsm4(uint32_t (&r)[4], uint32_t a) {
  asm volatile("ldmatrix.sync.aligned.m8n8.x4.shared.b16 {%0,%1,%2,%3}, [%4];" : "=r"(r[0]), "=r"(r[1]), "=r"(r[2]), "=r"(r[3]) : "r"(a) : "memory");
}
__device__ __forceinline__ void ldsm4t(uint32_t (&r)[4], uint32_t a) {
  asm volatile("ldmatrix.sync.aligned.m8n8.x4.trans.shared.b16 {%0,%1,%2,%3}, [%4];" : "=r"(r[0]), "=r"(r[1]), "=r"(r[2]), "=r"(r[3]) : "r"(a) : "memory");
}
__device__ __forceinline__ void stsm4(uint32_t a, uint32_t r0, uint32_t r1, uint32_t r2, uint32_t r3) {
  asm volatile("stmatrix.sync.aligned.m8n8.x4.shared.b16 [%0], {%1,%2,%3,%4};" ::"r"(a), "r"(r0), "r"(r1), "r"(r2), "r"(r3) : "memory");
}
__device__ __forceinline__ uint32_t pk2(float lo, float hi) { uint32_t r; asm("cvt.rn.bf16x2.f32 %0, %1, %2;" : "=r"(r) : "f"(hi), "f"(lo)); return r; }
__device__ __forceinline__ uint32_t hmul(uint32_t a, uint32_t b) { uint32_t r; asm("mul.rn.bf16x2 %0, %1, %2;" : "=r"(r) : "r"(a), "r"(b)); return r; }
__device__ __forceinline__ uint32_t hadd(uint32_t a, uint32_t b) { uint32_t r; asm("add.rn.bf16x2 %0, %1, %2;" : "=r"(r) : "r"(a), "r"(b)); return r; }
__device__ __forceinline__ uint32_t hmax(uint32_t a, uint32_t b) { uint32_t r; asm("max.bf16x2 %0, %1, %2;" : "=r"(r) : "r"(a), "r"(b)); return r; }
__device__ __forceinline__ uint32_t hmin(uint32_t a, uint32_t b) { uint32_t r; asm("min.bf16x2 %0, %1, %2;" : "=r"(r) : "r"(a), "r"(b)); return r; }
__device__ __forceinline__ float ex2(float x) { float r; asm("ex2.approx.ftz.f32 %0, %1;" : "=f"(r) : "f"(x)); return r; }
__device__ __forceinline__ uint32_t phi2(float lo, float hi) {
  uint32_t t = pk2(lo, hi);
  uint32_t e = pk2(ex2(lo * 1.4426950408889634f), ex2(hi * 1.4426950408889634f));
  return hadd(hmax(t, 0x35863586u), hmin(e, 0x3F803F80u));
}
__device__ __forceinline__ void poll_ge(const unsigned* p, unsigned target) {
  for (int n = 0; n < SPIN_LIMIT; n++) {
    unsigned v;
    asm volatile("ld.acquire.gpu.global.u32 %0, [%1];" : "=r"(v) : "l"(p) : "memory");
    if ((int)(v - target) >= 0) return;
  }
  __trap();
}

struct Params {
  CUtensorMap tmX, tmW, tmWo, tmK, tmV, tmQ, tmH, tmOA, tmOB;
  const __nv_bfloat16 *q, *k, *v, *shift_k, *h, *D, *wo;
};

__global__ void __cluster_dims__(2, 1, 1) __launch_bounds__(384, 1) fused_kernel(const __grid_constant__ Params P) {
  extern __shared__ __align__(1024) uint8_t smem[];
  const uint32_t sb = smem_u32(smem);
  const uint32_t bars = sb + OFF_BAR;
  const int tid = threadIdx.x, warp = tid >> 5, lane = tid & 31;
  const int rank = blockIdx.x & 1, cl = blockIdx.x >> 1;
  const int mb = cl >> 3, hq = cl & 7;
  const int hp = 2 * hq + rank;
  const int rb = 2 * mb + (hq >> 2), cb = hq & 3;
  const int ch0 = blockIdx.x * 8;
#define BAR(i) (bars + 8 * (i))

  if (tid == 0) STAMP(0, 0);
  if (warp == 8) {
    for (int i = lane; i < B_COUNT; i += 32) {
      int cnt = 1;
      if (i >= B_EMPTY1 && i < B_EMPTY1 + 3) cnt = 4;
      if (i == B_XT) cnt = 4;
      if (i == B_KV) cnt = 2;
      if (i == B_Y || i == B_PKFREE || i == B_ODONE) cnt = 8;
      if (i >= B_HFREE && i <= B_VFREE) cnt = 4;
      if (i >= B_FULL2) cnt = 2;
      if (i >= B_CONS2 && i <= B_CONS2 + 10) cnt = 4;
      mbar_init(BAR(i), cnt);
    }
    asm volatile("fence.mbarrier_init.release.cluster;" ::: "memory");
  }
  asm volatile("barrier.cluster.arrive.relaxed.aligned;\nbarrier.cluster.wait.aligned;" ::: "memory");

  if (warp < 8) {
    asm volatile("setmaxnreg.inc.sync.aligned.u32 224;");
    const int wg = warp >> 2, w = warp & 3, g = lane >> 2, q = lane & 3, t = tid & 127;
    const bool elect = (t == 0);
    uint32_t pq[2][16];
    {
      float acc[2][96];
      int st = 0, ph = 0;
      for (int kb = 0; kb < 16; kb++) {
        mbar_wait(BAR(B_FULL1 + st), ph);
        if (kb == 0 && elect) STAMP(wg, 1);
        const uint32_t sa = sb + st * STAGE_BYTES;
        const uint64_t da = mkdesc(sa + wg * 16384, 16, 1024, 1), db = mkdesc(sa + 32768, 8192, 1024, 1);
        wg_fence();
#pragma unroll
        for (int ks = 0; ks < 4; ks++) {
          wgmma_ss_n192<0, 1>(acc[0], da + ks * 2, db + ks * 128, (kb | ks) != 0);
          wgmma_ss_n192<0, 1>(acc[1], da + 512 + ks * 2, db + ks * 128, (kb | ks) != 0);
        }
        wg_commit();
        wg_wait<1>();
        if (kb > 0 && t < 2) mbar_arrive_cl(BAR(B_EMPTY1 + (st == 0 ? 2 : st - 1)), t);
        if (++st == 3) { st = 0; ph ^= 1; }
      }
      wg_wait<0>();
      keep(acc[0]); keep(acc[1]);
      if (t < 2) mbar_arrive_cl(BAR(B_EMPTY1 + 0), t);
      if (elect) STAMP(wg, 2);
      const uint32_t lrow = (16 * w + 8 * ((lane >> 3) & 1) + (lane & 7)) * 128 + (((lane >> 4) ^ (lane & 7)) << 4);
      const uint32_t pkb = sb + OFF_PK + wg * 16384, vb = sb + OFF_V + wg * 16384;
#pragma unroll
      for (int mt = 0; mt < 2; mt++)
#pragma unroll
        for (int cp = 0; cp < 4; cp++) {
          const float* a = &acc[mt][32 + 8 * cp];
          const float* b = &acc[mt][64 + 8 * cp];
          const uint32_t o = (lrow ^ (cp * 32)) + mt * 8192;
          stsm4(pkb + o, phi2(a[0], a[1]), phi2(a[2], a[3]), phi2(a[4], a[5]), phi2(a[6], a[7]));
          stsm4(vb + o, pk2(b[0], b[1]), pk2(b[2], b[3]), pk2(b[4], b[5]), pk2(b[6], b[7]));
        }
      fence_async();
      mbar_wait(BAR(B_XT), 0);
      bar_sync(1 + wg);
      if (elect) STAMP(wg, 3);
      float kva[36];
      wg_fence();
#pragma unroll
      for (int ks = 0; ks < 8; ks++)
        wgmma_ss_n72<1, 1>(kva, mkdesc(pkb + ks * 2048, 16, 1024, 1), mkdesc(vb + ks * 2048, sb + OFF_ONES - (vb + ks * 2048), 1024, 1), ks != 0);
      wg_commit();
#pragma unroll
      for (int i = 0; i < 16; i++) pq[0][i] = phi2(acc[0][2 * i], acc[0][2 * i + 1]);
      wg_wait<0>();
      keep(kva);
      {
        const unsigned par = *(volatile unsigned*)(smem + OFF_BAR + 512) & 1;
        float* dst = &g_kv[par][hp][0];
#pragma unroll
        for (int c = 0; c < 4; c++) {
          float v0 = w < 2 ? kva[4 * c] : kva[16 + 4 * c], v1 = w < 2 ? kva[4 * c + 1] : kva[17 + 4 * c];
          float v2 = w < 2 ? kva[4 * c + 2] : kva[18 + 4 * c], v3 = w < 2 ? kva[4 * c + 3] : kva[19 + 4 * c];
          asm volatile("red.global.add.v4.f32 [%0], {%1,%2,%3,%4};" ::"l"(dst + (c * 128 + t) * 4), "f"(v0), "f"(v1), "f"(v2), "f"(v3) : "memory");
        }
        if (q < 2) asm volatile("red.global.add.f32 [%0], %1;" ::"l"(dst + 2048 + 16 * w + g + 8 * q), "f"(q ? kva[34] : kva[32]) : "memory");
        __syncwarp();
        if (lane == 0) mbar_arrive(BAR(B_PKFREE));
      }
      if (elect) STAMP(wg, 4);
#pragma unroll
      for (int i = 0; i < 16; i++) pq[1][i] = phi2(acc[1][2 * i], acc[1][2 * i + 1]);
    }
    uint32_t a1[2][4], a4[4][4];
    float twr[4], twi[4];
    {
      const uint4* ct = (const uint4*)c_thr + t;
#pragma unroll
      for (int s = 0; s < 2; s++) { uint4 u = __ldg(ct + s * 128); a1[s][0] = u.x; a1[s][1] = u.y; a1[s][2] = u.z; a1[s][3] = u.w; }
#pragma unroll
      for (int s = 0; s < 4; s++) { uint4 u = __ldg(ct + (2 + s) * 128); a4[s][0] = u.x; a4[s][1] = u.y; a4[s][2] = u.z; a4[s][3] = u.w; }
      uint4 u = __ldg(ct + 6 * 128), v = __ldg(ct + 7 * 128);
      twr[0] = __uint_as_float(u.x); twr[1] = __uint_as_float(u.y); twr[2] = __uint_as_float(u.z); twr[3] = __uint_as_float(u.w);
      twi[0] = __uint_as_float(v.x); twi[1] = __uint_as_float(v.y); twi[2] = __uint_as_float(v.z); twi[3] = __uint_as_float(v.w);
    }
    uint2 dd = __ldg((const uint2*)(P.D + ch0 + 4 * wg));
    if (q != 0) dd = make_uint2(0, 0);
    mbar_wait(BAR(B_EMPTY1 + 2), 0);
    if (elect) STAMP(wg, 5);
    const uint32_t vp = sb + OFF_VP + wg * 8192;
    const uint32_t vpl = vp + (16 * w + 8 * (lane >> 4) + (lane & 7)) * 128 + ((((lane >> 3) & 1) ^ (lane & 7)) << 4);
#pragma unroll 1
    for (int i = 0; i < 4; i++) {
      if (i == 2) {
        if (elect) STAMP(wg, 8);
        mbar_wait(BAR(B_KV), 0);
        if (elect) STAMP(wg, 9);
        float oa[4][20];
        wg_fence();
#pragma unroll
        for (int mt = 0; mt < 2; mt++)
#pragma unroll
          for (int hh = 0; hh < 2; hh++)
#pragma unroll
            for (int ks = 0; ks < 2; ks++) {
              const uint32_t* a = &pq[mt][8 * hh + 4 * ks];
              wgmma_rs_n40<1>(oa[2 * mt + hh], a[0], a[1], a[2], a[3], mkdesc(sb + OFF_KVB + hh * 2560 + ks * 256, 128, 512, 0), ks);
            }
        wg_commit();
        wg_wait<0>();
        uint4* ot = g_o + ((2 * mb + wg) * 16 + hp) * 1024 + (16 * w + g) * 8;
#pragma unroll
        for (int mt = 0; mt < 2; mt++)
#pragma unroll
          for (int hh = 0; hh < 2; hh++) {
            float (&o)[20] = oa[2 * mt + hh];
            keep(o);
            const uint32_t den = hadd(pk2(o[16], o[18]), 0x35863586u);
#pragma unroll
            for (int r = 0; r < 2; r++) {
              const float ri = __frcp_rn(__uint_as_float(r ? (den & 0xFFFF0000u) : (den << 16)));
              uint4 u;
              u.x = pk2(o[2 * r] * ri, o[2 * r + 1] * ri);
              u.y = pk2(o[4 + 2 * r] * ri, o[5 + 2 * r] * ri);
              u.z = pk2(o[8 + 2 * r] * ri, o[9 + 2 * r] * ri);
              u.w = pk2(o[12 + 2 * r] * ri, o[13 + 2 * r] * ri);
              __stcg(ot + (64 * mt + 8 * r) * 8 + ((4 * hh + q) ^ g), u);
            }
          }
        __syncwarp();
        if (lane == 0) mbar_arrive(BAR(B_ODONE));
        if (elect) STAMP(wg, 10);
      }
      const uint32_t xt = sb + OFF_XT + (4 * wg + i) * XT_STRIDE;
      const uint32_t hb = sb + OFF_H + (i >> 1) * 16384 + (2 * wg + (i & 1)) * 4096;
      if (!(i & 1)) mbar_wait(BAR(B_H + (i >> 1)), 0);
      float ux[32], uh[32];
      wg_fence();
#pragma unroll
      for (int s = 0; s < 2; s++) wgmma_rs_n64<1>(ux, a1[s][0], a1[s][1], a1[s][2], a1[s][3], mkdesc(xt + s * 256, 128, 512, 0), s);
      wg_commit();
#pragma unroll
      for (int s = 0; s < 2; s++) wgmma_rs_n64<1>(uh, a1[s][0], a1[s][1], a1[s][2], a1[s][3], mkdesc(hb + s * 512, 1024, 256, 3), s);
      wg_commit();
      float X[2][16], H[2][16];
      const uint64_t df = mkdesc(sb + OFF_F2F, 128, 512, 0), di = mkdesc(sb + OFF_F2I, 128, 512, 0);
      auto stage2 = [&](float (&u)[32], float (&Z)[2][16]) {
        uint32_t fr[8], fi[8];
#pragma unroll
        for (int c = 0; c < 8; c++) {
          const int h2 = 2 * (c & 1);
          const float r0 = u[4 * c], r1 = u[4 * c + 1], i0 = u[4 * c + 2], i1 = u[4 * c + 3];
          fr[c] = pk2(r0 * twr[h2] - i0 * twi[h2], r1 * twr[h2 + 1] - i1 * twi[h2 + 1]);
          fi[c] = pk2(r0 * twi[h2] + i0 * twr[h2], r1 * twi[h2 + 1] + i1 * twr[h2 + 1]);
        }
        wg_fence();
#pragma unroll
        for (int p = 0; p < 2; p++) {
          wgmma_rs_n32<0>(Z[p], fr[4 * p], fr[4 * p + 2], fr[4 * p + 1], fr[4 * p + 3], df, 0);
          wgmma_rs_n32<0>(Z[p], fi[4 * p], fi[4 * p + 2], fi[4 * p + 1], fi[4 * p + 3], df + 16, 1);
        }
        wg_commit();
      };
      wg_wait<1>();
      keep(ux);
      stage2(ux, X);
      wg_wait<1>();
      keep(uh);
      {
        const uint32_t dw = (i & 2) ? dd.y : dd.x;
        uh[0] += __uint_as_float((i & 1) ? (dw & 0xFFFF0000u) : (dw << 16));
      }
      stage2(uh, H);
      wg_wait<0>();
      keep(X[0]); keep(X[1]); keep(H[0]); keep(H[1]);
      float V[2][16];
      {
        uint32_t pr[4][2], pi[4][2];
#pragma unroll
        for (int j = 0; j < 4; j++)
#pragma unroll
          for (int c = 0; c < 2; c++) {
            float sr[2], si[2];
#pragma unroll
            for (int e = 0; e < 2; e++) {
              sr[e] = 0.f; si[e] = 0.f;
#pragma unroll
              for (int a = 0; a <= j; a++) {
                const int b = j - a;
                const float hr = H[a >> 1][4 * c + 2 * (a & 1) + e], hi = H[a >> 1][8 + 4 * c + 2 * (a & 1) + e];
                const float xr = X[b >> 1][4 * c + 2 * (b & 1) + e], xi = X[b >> 1][8 + 4 * c + 2 * (b & 1) + e];
                sr[e] = a == 0 ? hr * xr : fmaf(hr, xr, sr[e]);
                si[e] = a == 0 ? hr * xi : fmaf(hr, xi, si[e]);
                sr[e] = fmaf(-hi, xi, sr[e]);
                si[e] = fmaf(hi, xr, si[e]);
              }
            }
            pr[j][c] = pk2(sr[0], sr[1]);
            pi[j][c] = pk2(si[0], si[1]);
          }
        wg_fence();
#pragma unroll
        for (int p = 0; p < 2; p++) {
          wgmma_rs_n32<0>(V[p], pr[2 * p][0], pr[2 * p + 1][0], pr[2 * p][1], pr[2 * p + 1][1], di, 0);
          wgmma_rs_n32<0>(V[p], pi[2 * p][0], pi[2 * p + 1][0], pi[2 * p][1], pi[2 * p + 1][1], di + 16, 1);
        }
        wg_commit();
      }
      wg_wait<0>();
      keep(V[0]); keep(V[1]);
#pragma unroll
      for (int j = 0; j < 4; j++) {
        uint32_t wr[2], wi[2];
#pragma unroll
        for (int c = 0; c < 2; c++) {
          const float* vr = &V[j >> 1][4 * c + 2 * (j & 1)];
          const float* vi = vr + 8;
          wr[c] = pk2(vr[0] * twr[2 * c] + vi[0] * twi[2 * c], vr[1] * twr[2 * c + 1] + vi[1] * twi[2 * c + 1]);
          wi[c] = pk2(vi[0] * twr[2 * c] - vr[0] * twi[2 * c], vi[1] * twr[2 * c + 1] - vr[1] * twi[2 * c + 1]);
        }
        stsm4(vpl ^ (j * 32), wr[0], wr[1], wi[0], wi[1]);
      }
      fence_async();
      bar_sync(1 + wg);
      if ((i & 1) && t < 2) mbar_arrive_cl(BAR(B_HFREE + (i >> 1)), t);
      float y[32];
      wg_fence();
#pragma unroll
      for (int s = 0; s < 4; s++) wgmma_rs_n64<1>(y, a4[s][0], a4[s][1], a4[s][2], a4[s][3], mkdesc(vp + s * 2048, 16, 1024, 1), s);
      wg_commit();
      wg_wait<0>();
      keep(y);
      uint32_t yo[8];
#pragma unroll
      for (int c = 0; c < 8; c++)
        yo[c] = c < 2 ? pk2(y[4 * c], y[4 * c + 1]) : pk2(y[4 * c] + y[4 * c - 6], y[4 * c + 1] + y[4 * c - 5]);
      const uint32_t ya = xt + (lane >> 3) * 512 + (8 * w + (lane & 7)) * 16;
      stsm4(ya, yo[0], yo[1], yo[2], yo[3]);
      stsm4(ya + 2048, yo[4], yo[5], yo[6], yo[7]);
      bar_sync(1 + wg);
      if (elect) STAMP(wg, i < 2 ? 6 + i : 9 + i);
    }
    if (t < 2) mbar_arrive_cl(BAR(B_VFREE), t);
    __syncwarp();
    if (lane == 0) mbar_arrive(BAR(B_Y));
    {
      float acc[64];
      for (int kb = 0; kb < 16; kb++) {
        mbar_wait(BAR(B_FULL2 + kb), 0);
        if (kb == 0 && elect) STAMP(wg, 13);
        const uint32_t sa = sb + ((uint32_t)(SLOT_A >> (4 * kb)) & 15) * 16384 + wg * 8192;
        const uint32_t sbb = sb + ((uint32_t)(SLOT_B >> (4 * kb)) & 15) * 16384;
        const uint64_t da = mkdesc(sa, 16, 1024, 1), db = mkdesc(sbb, 8192, 1024, 1);
        wg_fence();
#pragma unroll
        for (int ks = 0; ks < 4; ks++) wgmma_ss_n128<0, 1>(acc, da + ks * 2, db + ks * 128, (kb | ks) != 0);
        wg_commit();
        wg_wait<1>();
        if (kb > 0 && t < 2 && (kb <= 11 || t == rank)) mbar_arrive_cl(BAR(B_CONS2 + kb - 1), t);
      }
      wg_wait<0>();
      keep(acc);
      if (elect) STAMP(wg, 14);
      mbar_wait(BAR(B_CONS2 + 12), 0);
      const uint32_t stg = sb + (wg ? 9 : 3) * 16384;
      const uint32_t lrow = stg + (16 * w + 8 * ((lane >> 3) & 1) + (lane & 7)) * 128 + (((lane >> 4) ^ (lane & 7)) << 4);
#pragma unroll
      for (int cp = 0; cp < 8; cp++) {
        const float* a = &acc[8 * cp];
        stsm4((lrow ^ ((cp & 3) * 32)) + (cp >> 2) * 8192, pk2(a[0], a[1]), pk2(a[2], a[3]), pk2(a[4], a[5]), pk2(a[6], a[7]));
      }
      fence_async();
      bar_sync(1 + wg);
      if (elect) {
        const int col = 1024 + 256 * cb + 128 * rank, row = 128 * rb + 64 * wg;
        tma2d_st(&P.tmOB, stg, col, row);
        tma2d_st(&P.tmOB, stg + 8192, col + 64, row);
        asm volatile("cp.async.bulk.commit_group;\ncp.async.bulk.wait_group.read 0;" ::: "memory");
        STAMP(wg, 15);
      }
    }
  } else {
    asm volatile("setmaxnreg.dec.sync.aligned.u32 56;");
    if (warp == 8) {
      if (lane == 0) {
        int st = 0, ph = 1;
        for (int kb = 0; kb < 16; kb++) {
          if (kb >= 3) mbar_wait(BAR(B_EMPTY1 + st), ph);
          const uint32_t sa = sb + st * STAGE_BYTES;
          mbar_expect(BAR(B_FULL1 + st), STAGE_BYTES);
          tma2d_mc(sa + rank * 16384, &P.tmX, kb * 64, mb * 256 + rank * 128, BAR(B_FULL1 + st));
          tma3d(sa + 32768, &P.tmW, hp * 64, kb * 64, 0, BAR(B_FULL1 + st));
          if (kb == 2) { mbar_expect(BAR(B_XT), 6144); bulk_ld(sb + OFF_ONES, c_img, 6144, BAR(B_XT)); }
          if (++st == 3) { st = 0; ph ^= 1; }
        }
        STAMP(2, 1);
        const unsigned epoch = g_epoch[blockIdx.x];
        auto loadB = [&](int kb) {
          mbar_expect(BAR(B_FULL2 + kb), 16384);
          tma3d(sb + ((uint32_t)(SLOT_B >> (4 * kb)) & 15) * 16384, &P.tmWo, 0, kb * 64, 4 * cb + 2 * rank, BAR(B_FULL2 + kb));
        };
        auto loadA = [&](int kb) {
          mbar_expect(BAR(B_FULL2 + kb), 16384);
          bulk_ld_mc(sb + ((uint32_t)(SLOT_A >> (4 * kb)) & 15) * 16384 + rank * 8192, g_o + (rb * 16 + kb) * 1024 + rank * 512, 8192, BAR(B_FULL2 + kb));
        };
        mbar_wait(BAR(B_EMPTY1 + 1), 0);
        for (int i = 0; i < 4; i++) {
          if (!(i & 1)) mbar_expect(BAR(B_H + (i >> 1)), 16384);
          tma2d(sb + OFF_H + i * 8192, &P.tmH, 0, (ch0 + 4 * (i & 1) + (i & 2)) * 128, BAR(B_H + (i >> 1)));
        }
        loadB(0);
        mbar_wait(BAR(B_EMPTY1 + 0), 1);
        loadB(1); loadB(2);
        mbar_wait(BAR(B_PKFREE), 0);
        for (int kb = 3; kb < 7; kb++) loadB(kb);
        STAMP(2, 2);
        poll_ge(&g_ocnt[rb * 32], 16 * (epoch + 1));
        asm volatile("fence.proxy.async.global;" ::: "memory");
        STAMP(2, 3);
        for (int kb = 0; kb < 3; kb++) { mbar_wait(BAR(B_HFREE + kb), 0); loadA(kb); }
        STAMP(2, 4);
        for (int j = 0; j < 11; j++) {
          mbar_wait(BAR(B_CONS2 + j), 0);
          if (j < 2) { loadA(3 + 2 * j); loadA(4 + 2 * j); } else { loadA(j + 5); loadB(j + 5); }
        }
        g_epoch[blockIdx.x] = epoch + 1;
        STAMP(2, 5);
      }
    } else {
      const int hw = warp - 9, g = lane >> 2;
      const unsigned epoch = g_epoch[blockIdx.x];
      if (hw == 2) {
        if (lane == 0) {
          if (hp >= 3) { pf_t2d(&P.tmX, hp * 64, mb * 256); pf_t2d(&P.tmX, hp * 64, mb * 256 + 128); }
          if (mb >= 3) pf_t3d(&P.tmW, hp * 64, mb * 64, 0);
          pf_t3d(&P.tmW, hp * 64, (mb + 8) * 64, 0);
        }
        __nanosleep(1500);
        if (lane == 0) {
          pf_l2(P.k + blockIdx.x * 16384, 32768);
          pf_l2(P.v + blockIdx.x * 16384, 32768);
          pf_l2(P.h + blockIdx.x * 16384, 32768);
          pf_l2(P.wo + blockIdx.x * 8192, 16384);
          pf_l2(P.q + blockIdx.x * 16384, 32768);
          pf_l2(c_thr + blockIdx.x * 32, 128);
        }
      }
      if (hw == 0) {
        if (lane == 0) *(volatile unsigned*)(smem + OFF_BAR + 512) = epoch;
        float* z = &g_kv[(epoch & 1) ^ 1][hp][mb * 272];
        for (int i = lane; i < 272; i += 32) z[i] = 0.f;
      }
      uint32_t tap[4];
      {
        const uint2 u = __ldg((const uint2*)(P.shift_k + (ch0 + g) * 4));
        tap[0] = __byte_perm(u.x, 0, 0x1010); tap[1] = __byte_perm(u.x, 0, 0x3232);
        tap[2] = __byte_perm(u.y, 0, 0x1010); tap[3] = __byte_perm(u.y, 0, 0x3232);
      }
      __nanosleep(hw == 2 ? 2000 : 3500);
      if (lane == 0) STAMP(3, hw);
      const uint32_t stg = sb + OFF_STG + hw * STG_STRIDE;
      const uint32_t xtl = sb + OFF_XT + (lane & 7) * XT_STRIDE + ((lane >> 3) & 1) * 512 + (lane >> 4) * 16;
      int ph = 0;
      for (int ci = hw; ci < 16; ci += 3) {
        if (lane == 0) {
          mbar_expect(BAR(B_STG + 2 * hw), 2176 + 2048);
          tma2d(stg, &P.tmK, ch0, 128 * ci - 8, BAR(B_STG + 2 * hw));
          tma2d(stg + 2176, &P.tmV, ch0, 128 * ci, BAR(B_STG + 2 * hw));
        }
        mbar_wait(BAR(B_STG + 2 * hw), ph);
        ph ^= 1;
#pragma unroll 1
        for (int grp = 0; grp < 4; grp++) {
          uint32_t vv[4], o[4];
          ldsm4t(vv, stg + 2176 + (32 * grp + lane) * 16);
#pragma unroll
          for (int rg = 0; rg < 4; rg++) {
            uint32_t kk[4];
            ldsm4t(kk, stg + (8 + 32 * grp + 8 * rg + (lane & 7) - (lane >> 3)) * 16);
            uint32_t s = hadd(hadd(hadd(hmul(kk[3], tap[3]), hmul(kk[2], tap[2])), hmul(kk[1], tap[1])), hmul(kk[0], tap[0]));
            o[rg] = hmul(s, vv[rg]);
          }
          stsm4(xtl + (ci >> 2) * 1024 + ((ci & 3) * 8 + 2 * grp) * 16, o[0], o[1], o[2], o[3]);
        }
        __syncwarp();
      }
      fence_async();
      __syncwarp();
      if (lane == 0) {
        mbar_arrive(BAR(B_XT));
        STAMP(3, 3 + hw);
        for (int b = 0; b < 2; b++) {
          mbar_expect(BAR(B_STG + 2 * hw + b), 2048);
          tma2d(stg + b * 2048, &P.tmQ, ch0, 128 * (hw + 3 * b), BAR(B_STG + 2 * hw + b));
        }
      }
      if (hw == 2) {
        if (lane == 0) {
          mbar_wait(BAR(B_PKFREE), 0);
          __threadfence();
          atomicAdd(&g_kvcnt[hp * 32], 1);
          STAMP(3, 6);
          mbar_wait(BAR(B_ODONE), 0);
          __threadfence();
          atomicAdd(&g_ocnt[(2 * mb) * 32], 1);
          atomicAdd(&g_ocnt[(2 * mb + 1) * 32], 1);
          STAMP(3, 7);
        }
        __syncwarp();
      } else {
        if (lane == 0) { mbar_wait(BAR(B_PKFREE), 0); poll_ge(&g_kvcnt[hp * 32], 8 * (epoch + 1)); }
        __syncwarp();
        if (lane == 0 && hw == 0) STAMP(3, 8);
        const float* src = &g_kv[epoch & 1][hp][0];
        const int t = hw * 32 + lane;
        const float zf = __ldcg(src + 2048 + t);
#pragma unroll
        for (int hh = 0; hh < 2; hh++) {
          float4 f[4];
#pragma unroll
          for (int c = 0; c < 4; c++) f[c] = __ldcg((const float4*)src + c * 128 + hh * 64 + t);
          uint8_t* dst = smem + OFF_KVB + hh * 2560 + (lane & 3) * 512 + (16 * hw + g) * 16;
          *(uint4*)dst = make_uint4(pk2(f[0].x, f[0].y), pk2(f[1].x, f[1].y), pk2(f[2].x, f[2].y), pk2(f[3].x, f[3].y));
          *(uint4*)(dst + 128) = make_uint4(pk2(f[0].z, f[0].w), pk2(f[1].z, f[1].w), pk2(f[2].z, f[2].w), pk2(f[3].z, f[3].w));
        }
        const uint32_t zz = pk2(zf, zf);
        *(uint4*)(smem + OFF_KVB + hw * 2560 + 2048 + lane * 16) = make_uint4(zz, zz, zz, zz);
        fence_async();
        __syncwarp();
        if (lane == 0) { mbar_arrive(BAR(B_KV)); if (hw == 0) STAMP(3, 9); }
      }
      mbar_wait(BAR(B_Y), 0);
      int ph1 = 0, b = 0;
      for (int ci = hw; ci < 16; ci += 3) {
        const uint32_t qb = stg + b * 2048;
        mbar_wait(BAR(B_STG + 2 * hw + b), b ? ph1 : ph);
        if (b) ph1 ^= 1; else ph ^= 1;
#pragma unroll 1
        for (int grp = 0; grp < 4; grp++) {
          uint32_t yy[4], qq[4];
          ldsm4t(yy, xtl + (ci >> 2) * 1024 + ((ci & 3) * 8 + 2 * grp) * 16);
          ldsm4(qq, qb + (32 * grp + lane) * 16);
          stsm4(qb + (32 * grp + lane) * 16, hmul(yy[0], qq[0]), hmul(yy[1], qq[1]), hmul(yy[2], qq[2]), hmul(yy[3], qq[3]));
        }
        fence_async();
        __syncwarp();
        if (lane == 0) {
          tma2d_st(&P.tmOA, qb, ch0, 128 * ci);
          asm volatile("cp.async.bulk.commit_group;\ncp.async.bulk.wait_group.read 0;" ::: "memory");
          if (ci + 6 < 16) {
            mbar_expect(BAR(B_STG + 2 * hw + b), 2048);
            tma2d(qb, &P.tmQ, ch0, 128 * (ci + 6), BAR(B_STG + 2 * hw + b));
          }
        }
        b ^= 1;
      }
      if (lane == 0) STAMP(3, 10 + hw);
    }
  }
}

typedef CUresult (*EncodeFn)(CUtensorMap*, CUtensorMapDataType, cuuint32_t, void*, const cuuint64_t*, const cuuint64_t*,
                             const cuuint32_t*, const cuuint32_t*, CUtensorMapInterleave, CUtensorMapSwizzle,
                             CUtensorMapL2promotion, CUtensorMapFloatOOBfill);

static void enc(EncodeFn fn, CUtensorMap* m, const void* p, int rank, const cuuint64_t* dims, const cuuint64_t* strides,
                const cuuint32_t* box, CUtensorMapSwizzle swz, CUtensorMapL2promotion promo) {
  cuuint32_t es[3] = {1, 1, 1};
  fn(m, CU_TENSOR_MAP_DATA_TYPE_BFLOAT16, rank, (void*)p, dims, strides, box, es, CU_TENSOR_MAP_INTERLEAVE_NONE, swz, promo,
     CU_TENSOR_MAP_FLOAT_OOB_FILL_NONE);
}

extern "C" void kernel_launch(void* const* d_in, const int* in_sizes, int n_in, void* d_out, int out_size) {
  void* fp = nullptr;
  cudaDriverEntryPointQueryResult qr;
  cudaGetDriverEntryPoint("cuTensorMapEncodeTiled", &fp, cudaEnableDefault, &qr);
  EncodeFn fn = (EncodeFn)fp;
  Params P;
  P.q = (const __nv_bfloat16*)d_in[0]; P.k = (const __nv_bfloat16*)d_in[1]; P.v = (const __nv_bfloat16*)d_in[2];
  P.shift_k = (const __nv_bfloat16*)d_in[3]; P.h = (const __nv_bfloat16*)d_in[4]; P.D = (const __nv_bfloat16*)d_in[5];
  P.wo = (const __nv_bfloat16*)d_in[8];
  const CUtensorMapSwizzle S128 = CU_TENSOR_MAP_SWIZZLE_128B, S32 = CU_TENSOR_MAP_SWIZZLE_32B, S0 = CU_TENSOR_MAP_SWIZZLE_NONE;
  const CUtensorMapL2promotion P0 = CU_TENSOR_MAP_L2_PROMOTION_NONE, P128 = CU_TENSOR_MAP_L2_PROMOTION_L2_128B;
  { cuuint64_t d[2] = {1024, 2048}, s[1] = {2048}; cuuint32_t b[2] = {64, 128}; enc(fn, &P.tmX, d_in[6], 2, d, s, b, S128, P128); }
  { cuuint64_t d[3] = {1024, 1024, 3}, s[2] = {6144, 2048}; cuuint32_t b[3] = {64, 64, 3}; enc(fn, &P.tmW, d_in[7], 3, d, s, b, S128, P128); }
  { cuuint64_t d[3] = {64, 1024, 16}, s[2] = {2048, 128}; cuuint32_t b[3] = {64, 64, 2}; enc(fn, &P.tmWo, d_in[8], 3, d, s, b, S128, P128); }
  { cuuint64_t d[2] = {1024, 2048}, s[1] = {2048}; cuuint32_t b[2] = {8, 136}; enc(fn, &P.tmK, d_in[1], 2, d, s, b, S0, P0); }
  { cuuint64_t d[2] = {1024, 2048}, s[1] = {2048}; cuuint32_t b[2] = {8, 128};
    enc(fn, &P.tmV, d_in[2], 2, d, s, b, S0, P0); enc(fn, &P.tmQ, d_in[0], 2, d, s, b, S0, P0); }
  { cuuint64_t d[2] = {16, 131072}, s[1] = {32}; cuuint32_t b[2] = {16, 256}; enc(fn, &P.tmH, d_in[4], 2, d, s, b, S32, P128); }
  { cuuint64_t d[2] = {2048, 2048}, s[1] = {4096}; cuuint32_t b[2] = {8, 128}; enc(fn, &P.tmOA, d_out, 2, d, s, b, S0, P0); }
  { cuuint64_t d[2] = {2048, 2048}, s[1] = {4096}; cuuint32_t b[2] = {64, 64}; enc(fn, &P.tmOB, d_out, 2, d, s, b, S128, P0); }
  cudaFuncSetAttribute(fused_kernel, cudaFuncAttributeMaxDynamicSharedMemorySize, SMEM_TOTAL);
  fused_kernel<<<128, 384, SMEM_TOTAL>>>(P);
}
```

```cpp
#include <cuda_runtime.h>
#include <cuda_bf16.h>
#include <cuda.h>
#include <stdint.h>

template<int TA, int TB, int SA=1> __device__ __forceinline__ void wgmma_ss_n192(float (&d)[96], uint64_t da, uint64_t db, int scale_d) {
  asm volatile("{\n.reg .pred p;\nsetp.ne.b32 p, %98, 0;\n"
    "wgmma.mma_async.sync.aligned.m64n192k16.f32.bf16.bf16 {%0, %1, %2, %3, %4, %5, %6, %7, %8, %9, %10, %11, %12, %13, %14, %15, %16, %17, %18, %19, %20, %21, %22, %23, %24, %25, %26, %27, %28, %29, %30, %31, %32, %33, %34, %35, %36, %37, %38, %39, %40, %41, %42, %43, %44, %45, %46, %47, %48, %49, %50, %51, %52, %53, %54, %55, %56, %57, %58, %59, %60, %61, %62, %63, %64, %65, %66, %67, %68, %69, %70, %71, %72, %73, %74, %75, %76, %77, %78, %79, %80, %81, %82, %83, %84, %85, %86, %87, %88, %89, %90, %91, %92, %93, %94, %95}, %96, %97, p, %101, 1, %99, %100;\n}\n"
    : "+f"(d[0]), "+f"(d[1]), "+f"(d[2]), "+f"(d[3]), "+f"(d[4]), "+f"(d[5]), "+f"(d[6]), "+f"(d[7]), "+f"(d[8]), "+f"(d[9]), "+f"(d[10]), "+f"(d[11]), "+f"(d[12]), "+f"(d[13]), "+f"(d[14]), "+f"(d[15]), "+f"(d[16]), "+f"(d[17]), "+f"(d[18]), "+f"(d[19]), "+f"(d[20]), "+f"(d[21]), "+f"(d[22]), "+f"(d[23]), "+f"(d[24]), "+f"(d[25]), "+f"(d[26]), "+f"(d[27]), "+f"(d[28]), "+f"(d[29]), "+f"(d[30]), "+f"(d[31]), "+f"(d[32]), "+f"(d[33]), "+f"(d[34]), "+f"(d[35]), "+f"(d[36]), "+f"(d[37]), "+f"(d[38]), "+f"(d[39]), "+f"(d[40]), "+f"(d[41]), "+f"(d[42]), "+f"(d[43]), "+f"(d[44]), "+f"(d[45]), "+f"(d[46]), "+f"(d[47]), "+f"(d[48]), "+f"(d[49]), "+f"(d[50]), "+f"(d[51]), "+f"(d[52]), "+f"(d[53]), "+f"(d[54]), "+f"(d[55]), "+f"(d[56]), "+f"(d[57]), "+f"(d[58]), "+f"(d[59]), "+f"(d[60]), "+f"(d[61]), "+f"(d[62]), "+f"(d[63]), "+f"(d[64]), "+f"(d[65]), "+f"(d[66]), "+f"(d[67]), "+f"(d[68]), "+f"(d[69]), "+f"(d[70]), "+f"(d[71]), "+f"(d[72]), "+f"(d[73]), "+f"(d[74]), "+f"(d[75]), "+f"(d[76]), "+f"(d[77]), "+f"(d[78]), "+f"(d[79]), "+f"(d[80]), "+f"(d[81]), "+f"(d[82]), "+f"(d[83]), "+f"(d[84]), "+f"(d[85]), "+f"(d[86]), "+f"(d[87]), "+f"(d[88]), "+f"(d[89]), "+f"(d[90]), "+f"(d[91]), "+f"(d[92]), "+f"(d[93]), "+f"(d[94]), "+f"(d[95])
    : "l"(da), "l"(db), "r"(scale_d), "n"(TA), "n"(TB), "n"(SA));
}
template<int TA, int TB, int SA=1> __device__ __forceinline__ void wgmma_ss_n128(float (&d)[64], uint64_t da, uint64_t db, int scale_d) {
  asm volatile("{\n.reg .pred p;\nsetp.ne.b32 p, %66, 0;\n"
    "wgmma.mma_async.sync.aligned.m64n128k16.f32.bf16.bf16 {%0, %1, %2, %3, %4, %5, %6, %7, %8, %9, %10, %11, %12, %13, %14, %15, %16, %17, %18, %19, %20, %21, %22, %23, %24, %25, %26, %27, %28, %29, %30, %31, %32, %33, %34, %35, %36, %37, %38, %39, %40, %41, %42, %43, %44, %45, %46, %47, %48, %49, %50, %51, %52, %53, %54, %55, %56, %57, %58, %59, %60, %61, %62, %63}, %64, %65, p, %69, 1, %67, %68;\n}\n"
    : "+f"(d[0]), "+f"(d[1]), "+f"(d[2]), "+f"(d[3]), "+f"(d[4]), "+f"(d[5]), "+f"(d[6]), "+f"(d[7]), "+f"(d[8]), "+f"(d[9]), "+f"(d[10]), "+f"(d[11]), "+f"(d[12]), "+f"(d[13]), "+f"(d[14]), "+f"(d[15]), "+f"(d[16]), "+f"(d[17]), "+f"(d[18]), "+f"(d[19]), "+f"(d[20]), "+f"(d[21]), "+f"(d[22]), "+f"(d[23]), "+f"(d[24]), "+f"(d[25]), "+f"(d[26]), "+f"(d[27]), "+f"(d[28]), "+f"(d[29]), "+f"(d[30]), "+f"(d[31]), "+f"(d[32]), "+f"(d[33]), "+f"(d[34]), "+f"(d[35]), "+f"(d[36]), "+f"(d[37]), "+f"(d[38]), "+f"(d[39]), "+f"(d[40]), "+f"(d[41]), "+f"(d[42]), "+f"(d[43]), "+f"(d[44]), "+f"(d[45]), "+f"(d[46]), "+f"(d[47]), "+f"(d[48]), "+f"(d[49]), "+f"(d[50]), "+f"(d[51]), "+f"(d[52]), "+f"(d[53]), "+f"(d[54]), "+f"(d[55]), "+f"(d[56]), "+f"(d[57]), "+f"(d[58]), "+f"(d[59]), "+f"(d[60]), "+f"(d[61]), "+f"(d[62]), "+f"(d[63])
    : "l"(da), "l"(db), "r"(scale_d), "n"(TA), "n"(TB), "n"(SA));
}
template<int TA, int TB, int SA=1> __device__ __forceinline__ void wgmma_ss_n72(float (&d)[36], uint64_t da, uint64_t db, int scale_d) {
  asm volatile("{\n.reg .pred p;\nsetp.ne.b32 p, %38, 0;\n"
    "wgmma.mma_async.sync.aligned.m64n72k16.f32.bf16.bf16 {%0, %1, %2, %3, %4, %5, %6, %7, %8, %9, %10, %11, %12, %13, %14, %15, %16, %17, %18, %19, %20, %21, %22, %23, %24, %25, %26, %27, %28, %29, %30, %31, %32, %33, %34, %35}, %36, %37, p, %41, 1, %39, %40;\n}\n"
    : "+f"(d[0]), "+f"(d[1]), "+f"(d[2]), "+f"(d[3]), "+f"(d[4]), "+f"(d[5]), "+f"(d[6]), "+f"(d[7]), "+f"(d[8]), "+f"(d[9]), "+f"(d[10]), "+f"(d[11]), "+f"(d[12]), "+f"(d[13]), "+f"(d[14]), "+f"(d[15]), "+f"(d[16]), "+f"(d[17]), "+f"(d[18]), "+f"(d[19]), "+f"(d[20]), "+f"(d[21]), "+f"(d[22]), "+f"(d[23]), "+f"(d[24]), "+f"(d[25]), "+f"(d[26]), "+f"(d[27]), "+f"(d[28]), "+f"(d[29]), "+f"(d[30]), "+f"(d[31]), "+f"(d[32]), "+f"(d[33]), "+f"(d[34]), "+f"(d[35])
    : "l"(da), "l"(db), "r"(scale_d), "n"(TA), "n"(TB), "n"(SA));
}
template<int TB, int SA=1> __device__ __forceinline__ void wgmma_rs_n64(float (&d)[32], uint32_t a0, uint32_t a1, uint32_t a2, uint32_t a3, uint64_t db, int scale_d) {
  asm volatile("{\n.reg .pred p;\nsetp.ne.b32 p, %37, 0;\n"
    "wgmma.mma_async.sync.aligned.m64n64k16.f32.bf16.bf16 {%0, %1, %2, %3, %4, %5, %6, %7, %8, %9, %10, %11, %12, %13, %14, %15, %16, %17, %18, %19, %20, %21, %22, %23, %24, %25, %26, %27, %28, %29, %30, %31}, {%32, %33, %34, %35}, %36, p, %39, 1, %38;\n}\n"
    : "+f"(d[0]), "+f"(d[1]), "+f"(d[2]), "+f"(d[3]), "+f"(d[4]), "+f"(d[5]), "+f"(d[6]), "+f"(d[7]), "+f"(d[8]), "+f"(d[9]), "+f"(d[10]), "+f"(d[11]), "+f"(d[12]), "+f"(d[13]), "+f"(d[14]), "+f"(d[15]), "+f"(d[16]), "+f"(d[17]), "+f"(d[18]), "+f"(d[19]), "+f"(d[20]), "+f"(d[21]), "+f"(d[22]), "+f"(d[23]), "+f"(d[24]), "+f"(d[25]), "+f"(d[26]), "+f"(d[27]), "+f"(d[28]), "+f"(d[29]), "+f"(d[30]), "+f"(d[31])
    : "r"(a0), "r"(a1), "r"(a2), "r"(a3), "l"(db), "r"(scale_d), "n"(TB), "n"(SA));
}
template<int TB, int SA=1> __device__ __forceinline__ void wgmma_rs_n40(float (&d)[20], uint32_t a0, uint32_t a1, uint32_t a2, uint32_t a3, uint64_t db, int scale_d) {
  asm volatile("{\n.reg .pred p;\nsetp.ne.b32 p, %25, 0;\n"
    "wgmma.mma_async.sync.aligned.m64n40k16.f32.bf16.bf16 {%0, %1, %2, %3, %4, %5, %6, %7, %8, %9, %10, %11, %12, %13, %14, %15, %16, %17, %18, %19}, {%20, %21, %22, %23}, %24, p, %27, 1, %26;\n}\n"
    : "+f"(d[0]), "+f"(d[1]), "+f"(d[2]), "+f"(d[3]), "+f"(d[4]), "+f"(d[5]), "+f"(d[6]), "+f"(d[7]), "+f"(d[8]), "+f"(d[9]), "+f"(d[10]), "+f"(d[11]), "+f"(d[12]), "+f"(d[13]), "+f"(d[14]), "+f"(d[15]), "+f"(d[16]), "+f"(d[17]), "+f"(d[18]), "+f"(d[19])
    : "r"(a0), "r"(a1), "r"(a2), "r"(a3), "l"(db), "r"(scale_d), "n"(TB), "n"(SA));
}
template<int TB, int SA=1> __device__ __forceinline__ void wgmma_rs_n32(float (&d)[16], uint32_t a0, uint32_t a1, uint32_t a2, uint32_t a3, uint64_t db, int scale_d) {
  asm volatile("{\n.reg .pred p;\nsetp.ne.b32 p, %21, 0;\n"
    "wgmma.mma_async.sync.aligned.m64n32k16.f32.bf16.bf16 {%0, %1, %2, %3, %4, %5, %6, %7, %8, %9, %10, %11, %12, %13, %14, %15}, {%16, %17, %18, %19}, %20, p, %23, 1, %22;\n}\n"
    : "+f"(d[0]), "+f"(d[1]), "+f"(d[2]), "+f"(d[3]), "+f"(d[4]), "+f"(d[5]), "+f"(d[6]), "+f"(d[7]), "+f"(d[8]), "+f"(d[9]), "+f"(d[10]), "+f"(d[11]), "+f"(d[12]), "+f"(d[13]), "+f"(d[14]), "+f"(d[15])
    : "r"(a0), "r"(a1), "r"(a2), "r"(a3), "l"(db), "r"(scale_d), "n"(TB), "n"(SA));
}

__device__ __align__(128) const uint32_t c_thr[4096] = {
  0x3f803f80,0xbd498000,0x3f673f6d,0xbedbbec4,0x3f7d3f7f,0xbe16bdc9,0x3f5c3f62,0xbf04bef1,0x3f783f7b,0xbe79be48,0x3f4e3f55,0xbf18bf0e,
  0x3f713f75,0xbeacbe95,0x3f3e3f46,0xbf2cbf22,0x3f7d3f80,0xbe168000,0x3e793ec4,0xbf78bf6d,0x3f673f75,0xbedbbe95,0xbd493dc9,0xbf80bf7f,
  0x3f3e3f55,0xbf2cbf0e,0xbeacbe48,0xbf71bf7b,0x3f043f22,0xbf5cbf46,0xbf18bef1,0xbf4ebf62,0x3f783f80,0xbe798000,0xbf18bec4,0xbf4ebf6d,
  0x3f3e3f62,0xbf2cbef1,0xbf67bf46,0xbedbbf22,0x3eac3f0e,0xbf71bf55,0xbf80bf7b,0x3d49be48,0xbe163dc9,0xbf7dbf7f,0xbf5cbf75,0x3f043e95,
  0x3f713f80,0xbeac8000,0xbf80bf6d,0xbd49bec4,0x3f043f46,0xbf5cbf22,0xbf4ebf75,0x3f183e95,0xbe163e48,0xbf7dbf7b,0xbe79bf0e,0x3f783f55,
  0xbf3ebef1,0xbf2cbf62,0x3edb3dc9,0x3f673f7f,0x3f673f80,0xbedb8000,0xbf2cbf6d,0x3f3e3ec4,0x3e793f22,0xbf78bf46,0x3e16be95,0x3f7d3f75,
  0xbf18be48,0xbf4ebf7b,0x3f5c3f0e,0x3f043f55,0xbf80bf62,0xbd49bef1,0x3f713f7f,0xbeac3dc9,0x3f5c3f80,0xbf048000,0x3e16bec4,0x3f7d3f6d,
  0xbd493ef1,0xbf80bf62,0x3f713f22,0x3eac3f46,0xbf67bf0e,0xbedbbf55,0x3f3e3f7b,0xbf2cbe48,0xbf4ebf7f,0x3f183dc9,0xbe793e95,0xbf78bf75,
  0x3f4e3f80,0xbf188000,0x3f5c3ec4,0x3f043f6d,0xbeac3e95,0xbf71bf75,0x3f3e3f7f,0xbf2cbdc9,0xbf80bf55,0x3d49bf0e,0xbedb3e48,0xbf67bf7b,
  0xbe79bf46,0x3f783f22,0xbf7dbf62,0x3e16bef1,0x3f3e3f80,0xbf2c8000,0x3f713f6d,0xbeac3ec4,0xbf183dc9,0xbf4ebf7f,0xbe793ef1,0xbf78bf62,
  0xbf5cbf7b,0x3f04be48,0xbf7dbf55,0x3e16bf0e,0x3edbbe95,0x3f673f75,0x3d49bf22,0x3f803f46,0x3f2c3f80,0xbf3e8000,0x3eac3f6d,0xbf71bec4,
  0xbf4ebdc9,0xbf18bf7f,0xbf78bef1,0xbe79bf62,0xbf04bf7b,0x3f5c3e48,0xbe16bf55,0x3f7d3f0e,0x3f673e95,0x3edb3f75,0x3f803f22,0x3d493f46,
  0x3f183f80,0xbf4e8000,0xbf043ec4,0xbf5cbf6d,0xbf71be95,0xbeacbf75,0xbf2cbf7f,0x3f3ebdc9,0xbd49bf55,0x3f803f0e,0x3f673e48,0x3edb3f7b,
  0x3f783f46,0xbe793f22,0x3e163f62,0xbf7dbef1,0x3f043f80,0xbf5c8000,0xbf7dbec4,0xbe16bf6d,0xbf80bef1,0xbd49bf62,0x3eacbf22,0x3f713f46,
  0x3edbbf0e,0x3f673f55,0x3f2c3f7b,0xbf3e3e48,0x3f183f7f,0xbf4e3dc9,0xbf78be95,0xbe79bf75,0x3edb3f80,0xbf678000,0xbf3ebf6d,0x3f2cbec4,
  0xbf78bf22,0x3e79bf46,0x3f7d3e95,0x3e163f75,0x3f4ebe48,0x3f183f7b,0xbf043f0e,0xbf5cbf55,0xbd493f62,0xbf80bef1,0xbeacbf7f,0x3f713dc9,
  0x3eac3f80,0xbf718000,0x3d49bf6d,0x3f803ec4,0xbf5cbf46,0x3f04bf22,0x3f183f75,0xbf4e3e95,0x3f7d3e48,0x3e163f7b,0xbf78bf0e,0x3e79bf55,
  0xbf2c3ef1,0xbf3ebf62,0x3f67bdc9,0x3edb3f7f,0x3e793f80,0xbf788000,0x3f4ebec4,0x3f183f6d,0xbf2cbf62,0x3f3ebef1,0xbedb3f46,0xbf67bf22,
  0x3f713f0e,0xbeac3f55,0xbd49bf7b,0x3f803e48,0xbf7dbdc9,0xbe16bf7f,0x3f043f75,0xbf5c3e95,0x3e163f80,0xbf7d8000,0x3f783ec4,0xbe793f6d,
  0xbedbbf75,0x3f67be95,0xbf80bdc9,0xbd49bf7f,0x3f2c3f55,0xbf3e3f0e,0x3f71be48,0x3eac3f7b,0xbf5cbf22,0x3f04bf46,0xbf4e3ef1,0xbf18bf62,
  0x3d493f80,0xbf808000,0x3edb3f6d,0xbf673ec4,0xbe16bf7f,0x3f7dbdc9,0xbf04bf62,0x3f5cbef1,0x3e793f7b,0xbf783e48,0x3f183f55,0xbf4e3f0e,
  0xbeacbf75,0x3f71be95,0xbf2cbf46,0x3f3ebf22,0xbd493f80,0xbf808000,0xbedb3f6d,0xbf67bec4,0x3e16bf7f,0x3f7d3dc9,0x3f04bf62,0x3f5c3ef1,
  0xbe793f7b,0xbf78be48,0xbf183f55,0xbf4ebf0e,0x3eacbf75,0x3f713e95,0x3f2cbf46,0x3f3e3f22,0xbe163f80,0xbf7d8000,0xbf783ec4,0xbe79bf6d,
  0x3edbbf75,0x3f673e95,0x3f80bdc9,0xbd493f7f,0xbf2c3f55,0xbf3ebf0e,0xbf71be48,0x3eacbf7b,0x3f5cbf22,0x3f043f46,0x3f4e3ef1,0xbf183f62,
  0xbe793f80,0xbf788000,0xbf4ebec4,0x3f18bf6d,0x3f2cbf62,0x3f3e3ef1,0x3edb3f46,0xbf673f22,0xbf713f0e,0xbeacbf55,0x3d49bf7b,0x3f80be48,
  0x3f7dbdc9,0xbe163f7f,0xbf043f75,0xbf5cbe95,0xbeac3f80,0xbf718000,0xbd49bf6d,0x3f80bec4,0x3f5cbf46,0x3f043f22,0xbf183f75,0xbf4ebe95,
  0xbf7d3e48,0x3e16bf7b,0x3f78bf0e,0x3e793f55,0x3f2c3ef1,0xbf3e3f62,0xbf67bdc9,0x3edbbf7f,0xbedb3f80,0xbf678000,0x3f3ebf6d,0x3f2c3ec4,
  0x3f78bf22,0x3e793f46,0xbf7d3e95,0x3e16bf75,0xbf4ebe48,0x3f18bf7b,0x3f043f0e,0xbf5c3f55,0x3d493f62,0xbf803ef1,0x3eacbf7f,0x3f71bdc9,
  0xbf043f80,0xbf5c8000,0x3f7dbec4,0xbe163f6d,0x3f80bef1,0xbd493f62,0xbeacbf22,0x3f71bf46,0xbedbbf0e,0x3f67bf55,0xbf2c3f7b,0xbf3ebe48,
  0xbf183f7f,0xbf4ebdc9,0x3f78be95,0xbe793f75,0xbf183f80,0xbf4e8000,0x3f043ec4,0xbf5c3f6d,0x3f71be95,0xbeac3f75,0x3f2cbf7f,0x3f3e3dc9,
  0x3d49bf55,0x3f80bf0e,0xbf673e48,0x3edbbf7b,0xbf783f46,0xbe79bf22,0xbe163f62,0xbf7d3ef1,0xbf2c3f80,0xbf3e8000,0xbeac3f6d,0xbf713ec4,
  0x3f4ebdc9,0xbf183f7f,0x3f78bef1,0xbe793f62,0x3f04bf7b,0x3f5cbe48,0x3e16bf55,0x3f7dbf0e,0xbf673e95,0x3edbbf75,0xbf803f22,0x3d49bf46,
  0xbf3e3f80,0xbf2c8000,0xbf713f6d,0xbeacbec4,0x3f183dc9,0xbf4e3f7f,0x3e793ef1,0xbf783f62,0x3f5cbf7b,0x3f043e48,0x3f7dbf55,0x3e163f0e,
  0xbedbbe95,0x3f67bf75,0xbd49bf22,0x3f80bf46,0xbf4e3f80,0xbf188000,0xbf5c3ec4,0x3f04bf6d,0x3eac3e95,0xbf713f75,0xbf3e3f7f,0xbf2c3dc9,
  0x3f80bf55,0x3d493f0e,0x3edb3e48,0xbf673f7b,0x3e79bf46,0x3f78bf22,0x3f7dbf62,0x3e163ef1,0xbf5c3f80,0xbf048000,0xbe16bec4,0x3f7dbf6d,
  0x3d493ef1,0xbf803f62,0xbf713f22,0x3eacbf46,0x3f67bf0e,0xbedb3f55,0xbf3e3f7b,0xbf2c3e48,0x3f4ebf7f,0x3f18bdc9,0x3e793e95,0xbf783f75,
  0xbf673f80,0xbedb8000,0x3f2cbf6d,0x3f3ebec4,0xbe793f22,0xbf783f46,0xbe16be95,0x3f7dbf75,0x3f18be48,0xbf4e3f7b,0xbf5c3f0e,0x3f04bf55,
  0x3f80bf62,0xbd493ef1,0xbf713f7f,0xbeacbdc9,0xbf713f80,0xbeac8000,0x3f80bf6d,0xbd493ec4,0xbf043f46,0xbf5c3f22,0x3f4ebf75,0x3f18be95,
  0x3e163e48,0xbf7d3f7b,0x3e79bf0e,0x3f78bf55,0x3f3ebef1,0xbf2c3f62,0xbedb3dc9,0x3f67bf7f,0xbf783f80,0xbe798000,0x3f18bec4,0xbf4e3f6d,
  0xbf3e3f62,0xbf2c3ef1,0x3f67bf46,0xbedb3f22,0xbeac3f0e,0xbf713f55,0x3f80bf7b,0x3d493e48,0x3e163dc9,0xbf7d3f7f,0x3f5cbf75,0x3f04be95,
  0xbf7d3f80,0xbe168000,0xbe793ec4,0xbf783f6d,0xbf673f75,0xbedb3e95,0x3d493dc9,0xbf803f7f,0xbf3e3f55,0xbf2c3f0e,0x3eacbe48,0xbf713f7b,
  0xbf043f22,0xbf5c3f46,0x3f18bef1,0xbf4e3f62,0xbf803f80,0xbd498000,0xbf673f6d,0xbedb3ec4,0xbf7d3f7f,0xbe163dc9,0xbf5c3f62,0xbf043ef1,
  0xbf783f7b,0xbe793e48,0xbf4e3f55,0xbf183f0e,0xbf713f75,0xbeac3e95,0xbf3e3f46,0xbf2c3f22,0x3f2c3f35,0xbf3ebf35,0x3eac3ec4,0xbf71bf6d,
  0x3f183f22,0xbf4ebf46,0x3e793e95,0xbf78bf75,0x3f043f0e,0xbf5cbf55,0x3e163e48,0xbf7dbf7b,0x3edb3ef1,0xbf67bf62,0x3d493dc9,0xbf80bf7f,
  0xbf4ebf35,0xbf18bf35,0xbf5cbf6d,0x3f043ec4,0xbf71bf62,0xbeacbef1,0xbf2cbf46,0x3f3e3f22,0xbf80bf7b,0xbd49be48,0xbedbbf0e,0x3f673f55,
  0xbf78bf7f,0x3e793dc9,0xbe16be95,0x3f7d3f75,0xbf04bf35,0x3f5c3f35,0x3f7d3f6d,0x3e163ec4,0xbd49be95,0x3f803f75,0x3f713f7f,0xbeacbdc9,
  0x3edb3e48,0x3f673f7b,0x3f2c3f55,0xbf3ebf0e,0x3f4e3f22,0x3f183f46,0x3e793ef1,0xbf78bf62,0x3f673f35,0x3edb3f35,0xbf2cbec4,0xbf3ebf6d,
  0x3f783f7f,0xbe793dc9,0xbf7dbf62,0xbe16bef1,0x3f183f55,0xbf4ebf0e,0xbf5cbf7b,0x3f043e48,0xbd493e95,0xbf80bf75,0xbeacbf22,0x3f713f46,
  0x3eac3f35,0xbf71bf35,0x3d49bec4,0x3f803f6d,0xbf04bdc9,0xbf5cbf7f,0x3f4e3ef1,0x3f183f62,0xbf7dbf55,0xbe16bf0e,0x3f783f7b,0xbe793e48,
  0xbf3ebf75,0x3f2c3e95,0x3edb3f46,0xbf67bf22,0xbf78bf35,0xbe79bf35,0x3f183f6d,0xbf4ebec4,0xbf2cbf75,0x3f3e3e95,0xbedb3dc9,0xbf67bf7f,
  0x3eacbe48,0x3f713f7b,0xbf80bf55,0xbd49bf0e,0x3f7d3f46,0x3e163f22,0xbf04bf62,0x3f5c3ef1,0xbe16bf35,0x3f7d3f35,0xbf78bf6d,0x3e79bec4,
  0x3f673ef1,0x3edb3f62,0xbd49bf22,0x3f803f46,0x3f2c3f7b,0xbf3ebe48,0x3f713f0e,0x3eac3f55,0xbf043dc9,0xbf5cbf7f,0x3f183f75,0xbf4ebe95,
  0x3f803f35,0x3d493f35,0x3f673ec4,0x3edb3f6d,0x3e163f46,0xbf7dbf22,0x3f043f75,0xbf5cbe95,0xbf78bf0e,0xbe79bf55,0xbf4ebe48,0xbf18bf7b,
  0xbeacbf62,0x3f713ef1,0xbf2cbf7f,0x3f3e3dc9,0xbd493f35,0xbf80bf35,0xbedb3ec4,0xbf67bf6d,0xbf7dbf46,0x3e16bf22,0xbf5cbf75,0x3f04be95,
  0x3e79bf0e,0x3f783f55,0x3f18be48,0x3f4e3f7b,0x3f713f62,0xbeac3ef1,0x3f3e3f7f,0xbf2c3dc9,0xbf7dbf35,0x3e16bf35,0xbe79bf6d,0x3f783ec4,
  0x3edbbef1,0x3f673f62,0x3f803f22,0xbd493f46,0x3f3e3f7b,0xbf2c3e48,0xbeac3f0e,0xbf71bf55,0xbf5cbdc9,0xbf04bf7f,0xbf4ebf75,0x3f18be95,
  0x3e79bf35,0x3f783f35,0x3f4e3f6d,0xbf183ec4,0x3f3e3f75,0xbf2c3e95,0xbf67bdc9,0xbedbbf7f,0xbf71be48,0xbeacbf7b,0x3d49bf55,0x3f803f0e,
  0x3e16bf46,0x3f7d3f22,0x3f5c3f62,0xbf043ef1,0x3f713f35,0xbeac3f35,0xbf80bec4,0xbd49bf6d,0xbf5c3dc9,0xbf04bf7f,0x3f18bef1,0x3f4e3f62,
  0x3e16bf55,0x3f7d3f0e,0x3e793f7b,0xbf78be48,0x3f2c3f75,0xbf3e3e95,0xbf67bf46,0x3edbbf22,0xbedb3f35,0xbf67bf35,0x3f3ebec4,0x3f2c3f6d,
  0xbe79bf7f,0x3f783dc9,0xbe163f62,0xbf7dbef1,0x3f4e3f55,0xbf183f0e,0xbf04bf7b,0x3f5cbe48,0xbf80be95,0xbd49bf75,0x3f713f22,0xbeac3f46,
  0xbf5cbf35,0x3f04bf35,0xbe163f6d,0xbf7dbec4,0x3f803e95,0xbd493f75,0xbeacbf7f,0x3f71bdc9,0xbf673e48,0xbedbbf7b,0x3f3e3f55,0xbf2c3f0e,
  0x3f18bf22,0x3f4e3f46,0xbf78bef1,0x3e79bf62,0x3f18bf35,0x3f4e3f35,0xbf04bf6d,0x3f5cbec4,0xbeac3f62,0xbf71bef1,0x3f3e3f46,0xbf2c3f22,
  0x3d49bf7b,0x3f803e48,0xbf67bf0e,0x3edbbf55,0x3e793f7f,0xbf783dc9,0x3f7d3e95,0xbe163f75,0x3f3e3f35,0xbf2c3f35,0x3f713ec4,0xbeac3f6d,
  0xbf4ebf22,0x3f18bf46,0xbf78be95,0x3e79bf75,0x3f5c3f0e,0xbf043f55,0x3f7d3e48,0xbe163f7b,0xbf67bef1,0x3edbbf62,0xbf80bdc9,0x3d49bf7f,
  0xbf3e3f35,0xbf2cbf35,0xbf713ec4,0xbeacbf6d,0x3f4ebf22,0x3f183f46,0x3f78be95,0x3e793f75,0xbf5c3f0e,0xbf04bf55,0xbf7d3e48,0xbe16bf7b,
  0x3f67bef1,0x3edb3f62,0x3f80bdc9,0x3d493f7f,0xbf18bf35,0x3f4ebf35,0x3f04bf6d,0x3f5c3ec4,0x3eac3f62,0xbf713ef1,0xbf3e3f46,0xbf2cbf22,
  0xbd49bf7b,0x3f80be48,0x3f67bf0e,0x3edb3f55,0xbe793f7f,0xbf78bdc9,0xbf7d3e95,0xbe16bf75,0x3f5cbf35,0x3f043f35,0x3e163f6d,0xbf7d3ec4,
  0xbf803e95,0xbd49bf75,0x3eacbf7f,0x3f713dc9,0x3f673e48,0xbedb3f7b,0xbf3e3f55,0xbf2cbf0e,0xbf18bf22,0x3f4ebf46,0x3f78bef1,0x3e793f62,
  0x3edb3f35,0xbf673f35,0xbf3ebec4,0x3f2cbf6d,0x3e79bf7f,0x3f78bdc9,0x3e163f62,0xbf7d3ef1,0xbf4e3f55,0xbf18bf0e,0x3f04bf7b,0x3f5c3e48,
  0x3f80be95,0xbd493f75,0xbf713f22,0xbeacbf46,0xbf713f35,0xbeacbf35,0x3f80bec4,0xbd493f6d,0x3f5c3dc9,0xbf043f7f,0xbf18bef1,0x3f4ebf62,
  0xbe16bf55,0x3f7dbf0e,0xbe793f7b,0xbf783e48,0xbf2c3f75,0xbf3ebe95,0x3f67bf46,0x3edb3f22,0xbe79bf35,0x3f78bf35,0xbf4e3f6d,0xbf18bec4,
  0xbf3e3f75,0xbf2cbe95,0x3f67bdc9,0xbedb3f7f,0x3f71be48,0xbeac3f7b,0xbd49bf55,0x3f80bf0e,0xbe16bf46,0x3f7dbf22,0xbf5c3f62,0xbf04bef1,
  0x3f7dbf35,0x3e163f35,0x3e79bf6d,0x3f78bec4,0xbedbbef1,0x3f67bf62,0xbf803f22,0xbd49bf46,0xbf3e3f7b,0xbf2cbe48,0x3eac3f0e,0xbf713f55,
  0x3f5cbdc9,0xbf043f7f,0x3f4ebf75,0x3f183e95,0x3d493f35,0xbf803f35,0x3edb3ec4,0xbf673f6d,0x3f7dbf46,0x3e163f22,0x3f5cbf75,0x3f043e95,
  0xbe79bf0e,0x3f78bf55,0xbf18be48,0x3f4ebf7b,0xbf713f62,0xbeacbef1,0xbf3e3f7f,0xbf2cbdc9,0xbf803f35,0x3d49bf35,0xbf673ec4,0x3edbbf6d,
  0xbe163f46,0xbf7d3f22,0xbf043f75,0xbf5c3e95,0x3f78bf0e,0xbe793f55,0x3f4ebe48,0xbf183f7b,0x3eacbf62,0x3f71bef1,0x3f2cbf7f,0x3f3ebdc9,
  0x3e16bf35,0x3f7dbf35,0x3f78bf6d,0x3e793ec4,0xbf673ef1,0x3edbbf62,0x3d49bf22,0x3f80bf46,0xbf2c3f7b,0xbf3e3e48,0xbf713f0e,0x3eacbf55,
  0x3f043dc9,0xbf5c3f7f,0xbf183f75,0xbf4e3e95,0x3f78bf35,0xbe793f35,0xbf183f6d,0xbf4e3ec4,0x3f2cbf75,0x3f3ebe95,0x3edb3dc9,0xbf673f7f,
  0xbeacbe48,0x3f71bf7b,0x3f80bf55,0xbd493f0e,0xbf7d3f46,0x3e16bf22,0x3f04bf62,0x3f5cbef1,0xbeac3f35,0xbf713f35,0xbd49bec4,0x3f80bf6d,
  0x3f04bdc9,0xbf5c3f7f,0xbf4e3ef1,0x3f18bf62,0x3f7dbf55,0xbe163f0e,0xbf783f7b,0xbe79be48,0x3f3ebf75,0x3f2cbe95,0xbedb3f46,0xbf673f22,
  0xbf673f35,0x3edbbf35,0x3f2cbec4,0xbf3e3f6d,0xbf783f7f,0xbe79bdc9,0x3f7dbf62,0xbe163ef1,0xbf183f55,0xbf4e3f0e,0x3f5cbf7b,0x3f04be48,
  0x3d493e95,0xbf803f75,0x3eacbf22,0x3f71bf46,0x3f04bf35,0x3f5cbf35,0xbf7d3f6d,0x3e16bec4,0x3d49be95,0x3f80bf75,0xbf713f7f,0xbeac3dc9,
  0xbedb3e48,0x3f67bf7b,0xbf2c3f55,0xbf3e3f0e,0xbf4e3f22,0x3f18bf46,0xbe793ef1,0xbf783f62,0x3f4ebf35,0xbf183f35,0x3f5cbf6d,0x3f04bec4,
  0x3f71bf62,0xbeac3ef1,0x3f2cbf46,0x3f3ebf22,0x3f80bf7b,0xbd493e48,0x3edbbf0e,0x3f67bf55,0x3f78bf7f,0x3e79bdc9,0x3e16be95,0x3f7dbf75,
  0xbf2c3f35,0xbf3e3f35,0xbeac3ec4,0xbf713f6d,0xbf183f22,0xbf4e3f46,0xbe793e95,0xbf783f75,0xbf043f0e,0xbf5c3f55,0xbe163e48,0xbf7d3f7b,
  0xbedb3ef1,0xbf673f62,0xbd493dc9,0xbf803f7f,0x3b003b00,0x00000000,0x80008000,0x3b00bb00,0x3b003b00,0x00000000,0x80008000,0x3b00bb00,
  0x3b003b00,0x00000000,0x80008000,0x3b00bb00,0x3b003b00,0x00000000,0x80008000,0x3b00bb00,0x3afd3b00,0x3996b8c9,0xb996b8c9,0x3afdbb00,
  0x3af13af8,0x3a2cb9f9,0xba2cb9f9,0x3af1baf8,0x3adc3ae7,0x3a84ba5b,0xba84ba5b,0x3adcbae7,0x3abe3ace,0x3aacba98,0xbaacba98,0x3abebace,
  0x3af53aff,0x3a15b949,0xba15b949,0x3af5baff,0x3ac63ae2,0x3aa2ba71,0xbaa2ba71,0x3ac6bae2,0x3a713aa2,0x3ae2bac6,0xbae2bac6,0x3a71baa2,
  0x39493a15,0x3affbaf5,0xbaffbaf5,0x3949ba15,0x3ae73afd,0x3a5bb996,0xba5bb996,0x3ae7bafd,0x3a843abe,0x3adcbaac,0xbadcbaac,0x3a84babe,
  0xb8c939f9,0x3b00baf8,0xbb00baf8,0xb8c9b9f9,0xba98ba2c,0x3acebaf1,0xbacebaf1,0xba983a2c,0x3ad53afb,0x3a8eb9c8,0xba8eb9c8,0x3ad5bafb,
  0x39c83a8e,0x3afbbad5,0xbafbbad5,0x39c8ba8e,0xba8eb9c8,0x3ad5bafb,0xbad5bafb,0xba8e39c8,0xbafbbad5,0x39c8ba8e,0xb9c8ba8e,0xbafb3ad5,
  0x3abe3af8,0x3aacb9f9,0xbaacb9f9,0x3abebaf8,0xb9963a2c,0x3afdbaf1,0xbafdbaf1,0xb996ba2c,0xbae7ba98,0x3a5bbace,0xba5bbace,0xbae73a98,
  0xbadcbb00,0xba8438c9,0x3a8438c9,0xbadc3b00,0x3aa23af5,0x3ac6ba15,0xbac6ba15,0x3aa2baf5,0xba713949,0x3ae2baff,0xbae2baff,0xba71b949,
  0xbaffbae2,0xb949ba71,0x3949ba71,0xbaff3ae2,0xba15bac6,0xbaf53aa2,0x3af53aa2,0xba153ac6,0x3a843af1,0x3adcba2c,0xbadcba2c,0x3a84baf1,
  0xbabeb996,0x3aacbafd,0xbaacbafd,0xbabe3996,0xbacebb00,0xba98b8c9,0x3a98b8c9,0xbace3b00,0x3a5bb9f9,0xbae73af8,0x3ae73af8,0x3a5b39f9,
  0x3a443aed,0x3aedba44,0xbaedba44,0x3a44baed,0xbaedba44,0x3a44baed,0xba44baed,0xbaed3a44,0xba44baed,0xbaed3a44,0x3aed3a44,0xba443aed,
  0x3aed3a44,0xba443aed,0x3a443aed,0x3aedba44,0x39f93ae7,0x3af8ba5b,0xbaf8ba5b,0x39f9bae7,0xbb00ba98,0x38c9bace,0xb8c9bace,0xbb003a98,
  0x3996baac,0xbafd3abe,0x3afd3abe,0x39963aac,0x3af13adc,0x3a2c3a84,0xba2c3a84,0x3af1badc,0x39493ae2,0x3affba71,0xbaffba71,0x3949bae2,
  0xbaf5bac6,0xba15baa2,0x3a15baa2,0xbaf53ac6,0x3aa2ba15,0xbac63af5,0x3ac63af5,0x3aa23a15,0x3a713aff,0x3ae2b949,0xbae2b949,0x3a71baff,
  0xb8c93adc,0x3b00ba84,0xbb00ba84,0xb8c9badc,0xbacebae7,0xba98ba5b,0x3a98ba5b,0xbace3ae7,0x3af13996,0xba2c3afd,0x3a2c3afd,0x3af1b996,
  0xb9f93abe,0x3af8baac,0xbaf8baac,0xb9f9babe,0xb9c83ad5,0x3afbba8e,0xbafbba8e,0xb9c8bad5,0xba8ebafb,0xbad5b9c8,0x3ad5b9c8,0xba8e3afb,
  0x3afb3a8e,0x39c83ad5,0xb9c83ad5,0x3afbba8e,0xbad539c8,0x3a8ebafb,0xba8ebafb,0xbad5b9c8,0xba2c3ace,0x3af1ba98,0xbaf1ba98,0xba2cbace,
  0xb9f9bb00,0xbaf838c9,0x3af838c9,0xb9f93b00,0x3abe3adc,0x3aac3a84,0xbaac3a84,0x3abebadc,0xbafdba5b,0xb996bae7,0x3996bae7,0xbafd3a5b,
  0xba713ac6,0x3ae2baa2,0xbae2baa2,0xba71bac6,0x3949baf5,0xbaff3a15,0x3aff3a15,0x39493af5,0x3a153aff,0x3af53949,0xbaf53949,0x3a15baff,
  0xbaa2bae2,0xbac6ba71,0x3ac6ba71,0xbaa23ae2,0xba983abe,0x3acebaac,0xbacebaac,0xba98babe,0x3a5bbadc,0xbae73a84,0x3ae73a84,0x3a5b3adc,
  0xb9f93af1,0x3af8ba2c,0xbaf8ba2c,0xb9f9baf1,0x38c9bafd,0xbb003996,0x3b003996,0x38c93afd,0xbab53ab5,0x3ab5bab5,0xbab5bab5,0xbab5bab5,
  0x3ab5bab5,0xbab53ab5,0x3ab53ab5,0x3ab53ab5,0xbab53ab5,0x3ab5bab5,0xbab5bab5,0xbab5bab5,0x3ab5bab5,0xbab53ab5,0x3ab53ab5,0x3ab53ab5,
  0xbace3aac,0x3a98babe,0xba98babe,0xbacebaac,0x3ae7ba84,0xba5b3adc,0x3a5b3adc,0x3ae73a84,0xbaf83a2c,0x39f9baf1,0xb9f9baf1,0xbaf8ba2c,
  0x3b00b996,0xb8c93afd,0x38c93afd,0x3b003996,0xbae23aa2,0x3a71bac6,0xba71bac6,0xbae2baa2,0x3affba15,0xb9493af5,0x39493af5,0x3aff3a15,
  0xbaf5b949,0xba15baff,0x3a15baff,0xbaf53949,0x3ac63a71,0x3aa23ae2,0xbaa23ae2,0x3ac6ba71,0xbaf13a98,0x3a2cbace,0xba2cbace,0xbaf1ba98,
  0x3af8b8c9,0x39f93b00,0xb9f93b00,0x3af838c9,0xbaacba84,0xbabebadc,0x3abebadc,0xbaac3a84,0x39963ae7,0x3afd3a5b,0xbafd3a5b,0x3996bae7,
  0xbafb3a8e,0x39c8bad5,0xb9c8bad5,0xbafbba8e,0x3ad539c8,0x3a8e3afb,0xba8e3afb,0x3ad5b9c8,0xb9c8bad5,0xbafbba8e,0x3afbba8e,0xb9c83ad5,
  0xba8e3afb,0x3ad5b9c8,0xbad5b9c8,0xba8ebafb,0xbb003a84,0x38c9badc,0xb8c9badc,0xbb00ba84,0x3a983a5b,0x3ace3ae7,0xbace3ae7,0x3a98ba5b,
  0x3a2cbafd,0xbaf1b996,0x3af1b996,0x3a2c3afd,0xbaf83aac,0x39f9babe,0xb9f9babe,0xbaf8baac,0xbaff3a71,0xb949bae2,0x3949bae2,0xbaffba71,
  0x3a153aa2,0x3af53ac6,0xbaf53ac6,0x3a15baa2,0x3ac6baf5,0xbaa23a15,0x3aa23a15,0x3ac63af5,0xbae23949,0xba71baff,0x3a71baff,0xbae2b949,
  0xbaf83a5b,0xb9f9bae7,0x39f9bae7,0xbaf8ba5b,0xb8c93ace,0x3b003a98,0xbb003a98,0xb8c9bace,0x3afdbabe,0xb9963aac,0x39963aac,0x3afd3abe,
  0xba2cba84,0xbaf1badc,0x3af1badc,0xba2c3a84,0xbaed3a44,0xba44baed,0x3a44baed,0xbaedba44,0xba443aed,0x3aed3a44,0xbaed3a44,0xba44baed,
  0x3aedba44,0x3a443aed,0xba443aed,0x3aed3a44,0x3a44baed,0xbaedba44,0x3aedba44,0x3a443aed,0xbadc3a2c,0xba84baf1,0x3a84baf1,0xbadcba2c,
  0xbaac3afd,0x3abe3996,0xbabe3996,0xbaacbafd,0x3a9838c9,0x3ace3b00,0xbace3b00,0x3a98b8c9,0x3ae7baf8,0xba5b39f9,0x3a5b39f9,0x3ae73af8,
  0xbac63a15,0xbaa2baf5,0x3aa2baf5,0xbac6ba15,0xbae23aff,0x3a71b949,0xba71b949,0xbae2baff,0x39493a71,0x3aff3ae2,0xbaff3ae2,0x3949ba71,
  0x3af5baa2,0x3a153ac6,0xba153ac6,0x3af53aa2,0xbaac39f9,0xbabebaf8,0x3abebaf8,0xbaacb9f9,0xbafd3af1,0x3996ba2c,0xb996ba2c,0xbafdbaf1,
  0xba5b3ace,0x3ae73a98,0xbae73a98,0xba5bbace,0x3a84b8c9,0x3adc3b00,0xbadc3b00,0x3a8438c9,0xba8e39c8,0xbad5bafb,0x3ad5bafb,0xba8eb9c8,
  0xbafb3ad5,0xb9c8ba8e,0x39c8ba8e,0xbafbbad5,0xbad53afb,0x3a8e39c8,0xba8e39c8,0xbad5bafb,0xb9c83a8e,0x3afb3ad5,0xbafb3ad5,0xb9c8ba8e,
  0xba5b3996,0xbae7bafd,0x3ae7bafd,0xba5bb996,0xbadc3aac,0xba84babe,0x3a84babe,0xbadcbaac,0xbb003af8,0x38c9b9f9,0xb8c9b9f9,0xbb00baf8,
  0xbace3af1,0x3a983a2c,0xba983a2c,0xbacebaf1,0xba153949,0xbaf5baff,0x3af5baff,0xba15b949,0xbaa23a71,0xbac6bae2,0x3ac6bae2,0xbaa2ba71,
  0xbae23ac6,0xba71baa2,0x3a71baa2,0xbae2bac6,0xbaff3af5,0xb949ba15,0x3949ba15,0xbaffbaf5,0xb99638c9,0xbafdbb00,0x3afdbb00,0xb996b8c9,
  0xba2c39f9,0xbaf1baf8,0x3af1baf8,0xba2cb9f9,0xba843a5b,0xbadcbae7,0x3adcbae7,0xba84ba5b,0xbaac3a98,0xbabebace,0x3abebace,0xbaacba98,
  0x3b003b00,0x00000000,0x80008000,0x3b00bb00,0x3b003b00,0x00000000,0x80008000,0x3b00bb00,0x3b003b00,0x00000000,0x80008000,0x3b00bb00,
  0x3b003b00,0x00000000,0x80008000,0x3b00bb00,0x3a983aac,0x3acebabe,0xbacebabe,0x3a98baac,0x3a5b3a84,0x3ae7badc,0xbae7badc,0x3a5bba84,
  0x39f93a2c,0x3af8baf1,0xbaf8baf1,0x39f9ba2c,0x38c93996,0x3b00bafd,0xbb00bafd,0x38c9b996,0xba15b949,0x3af5baff,0xbaf5baff,0xba153949,
  0xbaa2ba71,0x3ac6bae2,0xbac6bae2,0xbaa23a71,0xbae2bac6,0x3a71baa2,0xba71baa2,0xbae23ac6,0xbaffbaf5,0x3949ba15,0xb949ba15,0xbaff3af5,
  0xbaf1bace,0x3a2cba98,0xba2cba98,0xbaf13ace,0xbaf8bb00,0xb9f9b8c9,0x39f9b8c9,0xbaf83b00,0xbaacbadc,0xbabe3a84,0x3abe3a84,0xbaac3adc,
  0xb996ba5b,0xbafd3ae7,0x3afd3ae7,0xb9963a5b,0xbad5bafb,0xba8e39c8,0x3a8e39c8,0xbad53afb,0xb9c8ba8e,0xbafb3ad5,0x3afb3ad5,0xb9c83a8e,
  0x3a8e39c8,0xbad53afb,0x3ad53afb,0x3a8eb9c8,0x3afb3ad5,0xb9c83a8e,0x39c83a8e,0x3afbbad5,0xb8c9ba84,0xbb003adc,0x3b003adc,0xb8c93a84,
  0x3ace3a5b,0xba983ae7,0x3a983ae7,0x3aceba5b,0x3af13afd,0x3a2c3996,0xba2c3996,0x3af1bafd,0x39f93aac,0x3af8babe,0xbaf8babe,0x39f9baac,
  0x3ac63a15,0xbaa23af5,0x3aa23af5,0x3ac6ba15,0x3ae23aff,0x3a713949,0xba713949,0x3ae2baff,0xb9493a71,0x3affbae2,0xbaffbae2,0xb949ba71,
  0xbaf5baa2,0x3a15bac6,0xba15bac6,0xbaf53aa2,0x3af83ae7,0x39f93a5b,0xb9f93a5b,0x3af8bae7,0xb8c93a98,0x3b00bace,0xbb00bace,0xb8c9ba98,
  0xbafdbaac,0x3996babe,0xb996babe,0xbafd3aac,0xba2cbadc,0xbaf13a84,0x3af13a84,0xba2c3adc,0x3a443aed,0x3aedba44,0xbaedba44,0x3a44baed,
  0xbaedba44,0x3a44baed,0xba44baed,0xbaed3a44,0xba44baed,0xbaed3a44,0x3aed3a44,0xba443aed,0x3aed3a44,0xba443aed,0x3a443aed,0x3aedba44,
  0xba843a2c,0x3adcbaf1,0xbadcbaf1,0xba84ba2c,0xbabebafd,0xbaacb996,0x3aacb996,0xbabe3afd,0x3ace38c9,0xba983b00,0x3a983b00,0x3aceb8c9,
  0x3a5b3af8,0x3ae7b9f9,0xbae7b9f9,0x3a5bbaf8,0xbaffba71,0x3949bae2,0xb949bae2,0xbaff3a71,0x3a15baa2,0xbaf53ac6,0x3af53ac6,0x3a153aa2,
  0x3ac63af5,0x3aa23a15,0xbaa23a15,0x3ac6baf5,0xbae2b949,0x3a71baff,0xba71baff,0xbae23949,0xbaacbaf8,0xbabeb9f9,0x3abeb9f9,0xbaac3af8,
  0x3afd3a2c,0xb9963af1,0x39963af1,0x3afdba2c,0xba5b3a98,0x3ae7bace,0xbae7bace,0xba5bba98,0xba84bb00,0xbadcb8c9,0x3adcb8c9,0xba843b00,
  0x39c8bad5,0xbafb3a8e,0x3afb3a8e,0x39c83ad5,0x3a8e3afb,0x3ad539c8,0xbad539c8,0x3a8ebafb,0xbafbba8e,0xb9c8bad5,0x39c8bad5,0xbafb3a8e,
  0x3ad5b9c8,0xba8e3afb,0x3a8e3afb,0x3ad539c8,0x3ae7b996,0xba5b3afd,0x3a5b3afd,0x3ae73996,0xba843aac,0x3adcbabe,0xbadcbabe,0xba84baac,
  0xb8c9baf8,0xbb0039f9,0x3b0039f9,0xb8c93af8,0x3a983af1,0x3ace3a2c,0xbace3a2c,0x3a98baf1,0x3ae23aa2,0x3a713ac6,0xba713ac6,0x3ae2baa2,
  0xbaffba15,0xb949baf5,0x3949baf5,0xbaff3a15,0x3af5b949,0xba153aff,0x3a153aff,0x3af53949,0xbac63a71,0x3aa2bae2,0xbaa2bae2,0xbac6ba71,
  0x39963b00,0x3afd38c9,0xbafd38c9,0x3996bb00,0xba2cbaf8,0xbaf1b9f9,0x3af1b9f9,0xba2c3af8,0x3a843ae7,0x3adc3a5b,0xbadc3a5b,0x3a84bae7,
  0xbaacbace,0xbabeba98,0x3abeba98,0xbaac3ace,0xbab53ab5,0x3ab5bab5,0xbab5bab5,0xbab5bab5,0x3ab5bab5,0xbab53ab5,0x3ab53ab5,0x3ab53ab5,
  0xbab53ab5,0x3ab5bab5,0xbab5bab5,0xbab5bab5,0x3ab5bab5,0xbab53ab5,0x3ab53ab5,0x3ab53ab5,0xbafdb8c9,0xb996bb00,0x3996bb00,0xbafd38c9,
  0x3af139f9,0x3a2c3af8,0xba2c3af8,0x3af1b9f9,0xbadcba5b,0xba84bae7,0x3a84bae7,0xbadc3a5b,0x3abe3a98,0x3aac3ace,0xbaac3ace,0x3abeba98,
  0xba71bac6,0xbae2baa2,0x3ae2baa2,0xba713ac6,0x39493af5,0x3aff3a15,0xbaff3a15,0x3949baf5,0x3a15baff,0xbaf53949,0x3af53949,0x3a153aff,
  0xbaa23ae2,0x3ac6ba71,0xbac6ba71,0xbaa2bae2,0x3a5bbafd,0xbae73996,0x3ae73996,0x3a5b3afd,0xbadc3abe,0x3a84baac,0xba84baac,0xbadcbabe,
  0x3b00b9f9,0x38c93af8,0xb8c93af8,0x3b0039f9,0xbaceba2c,0xba98baf1,0x3a98baf1,0xbace3a2c,0x3afbba8e,0xb9c83ad5,0x39c83ad5,0x3afb3a8e,
  0xbad5b9c8,0xba8ebafb,0x3a8ebafb,0xbad539c8,0x39c83ad5,0x3afb3a8e,0xbafb3a8e,0x39c8bad5,0x3a8ebafb,0xbad539c8,0x3ad539c8,0x3a8e3afb,
  0x3abe39f9,0x3aac3af8,0xbaac3af8,0x3abeb9f9,0x3996baf1,0xbafdba2c,0x3afdba2c,0x39963af1,0xbae73ace,0x3a5bba98,0xba5bba98,0xbae7bace,
  0x3adc38c9,0x3a843b00,0xba843b00,0x3adcb8c9,0xb9493ae2,0x3aff3a71,0xbaff3a71,0xb949bae2,0x3af5bac6,0xba153aa2,0x3a153aa2,0x3af53ac6,
  0xbaa2ba15,0xbac6baf5,0x3ac6baf5,0xbaa23a15,0xba713aff,0x3ae23949,0xbae23949,0xba71baff,0xbadc3af1,0x3a84ba2c,0xba84ba2c,0xbadcbaf1,
  0x3aac3996,0x3abe3afd,0xbabe3afd,0x3aacb996,0x3a98bb00,0xbaceb8c9,0x3aceb8c9,0x3a983b00,0xbae739f9,0xba5bbaf8,0x3a5bbaf8,0xbae7b9f9,
  0xbaed3a44,0xba44baed,0x3a44baed,0xbaedba44,0xba443aed,0x3aed3a44,0xbaed3a44,0xba44baed,0x3aedba44,0x3a443aed,0xba443aed,0x3aed3a44,
  0x3a44baed,0xbaedba44,0x3aedba44,0x3a443aed,0xb9f9ba5b,0xbaf8bae7,0x3af8bae7,0xb9f93a5b,0xbb003ace,0x38c9ba98,0xb8c9ba98,0xbb00bace,
  0xb9963abe,0x3afd3aac,0xbafd3aac,0xb996babe,0x3af1ba84,0x3a2c3adc,0xba2c3adc,0x3af13a84,0x3aa2baf5,0xbac6ba15,0x3ac6ba15,0x3aa23af5,
  0xba71b949,0xbae2baff,0x3ae2baff,0xba713949,0xbaff3ae2,0x3949ba71,0xb949ba71,0xbaffbae2,0xba153ac6,0x3af53aa2,0xbaf53aa2,0xba15bac6,
  0x3b00badc,0x38c93a84,0xb8c93a84,0x3b003adc,0x3a98bae7,0xbaceba5b,0x3aceba5b,0x3a983ae7,0xba2cb996,0xbaf1bafd,0x3af1bafd,0xba2c3996,
  0xbaf83abe,0xb9f9baac,0x39f9baac,0xbaf8babe,0x3a8eb9c8,0x3ad53afb,0xbad53afb,0x3a8e39c8,0x3afbbad5,0x39c83a8e,0xb9c83a8e,0x3afb3ad5,
  0x3ad5bafb,0xba8eb9c8,0x3a8eb9c8,0x3ad53afb,0x39c8ba8e,0xbafbbad5,0x3afbbad5,0x39c83a8e,0xba2c3a98,0x3af13ace,0xbaf13ace,0xba2cba98,
  0x39f938c9,0x3af83b00,0xbaf83b00,0x39f9b8c9,0x3abeba84,0x3aac3adc,0xbaac3adc,0x3abe3a84,0x3afdbae7,0x39963a5b,0xb9963a5b,0x3afd3ae7,
  0xbaf53aff,0x3a153949,0xba153949,0xbaf5baff,0xbac63ae2,0x3aa23a71,0xbaa23a71,0xbac6bae2,0xba713aa2,0x3ae23ac6,0xbae23ac6,0xba71baa2,
  0xb9493a15,0x3aff3af5,0xbaff3af5,0xb949ba15,0xbace3abe,0xba98baac,0x3a98baac,0xbacebabe,0xbae73adc,0xba5bba84,0x3a5bba84,0xbae7badc,
  0xbaf83af1,0xb9f9ba2c,0x39f9ba2c,0xbaf8baf1,0xbb003afd,0xb8c9b996,0x38c9b996,0xbb00bafd,0x3b003b00,0x00000000,0x80008000,0x3b00bb00,
  0x3b003b00,0x00000000,0x80008000,0x3b00bb00,0x3b003b00,0x00000000,0x80008000,0x3b00bb00,0x3b003b00,0x00000000,0x80008000,0x3b00bb00,
  0xb996b8c9,0x3afdbb00,0xbafdbb00,0xb99638c9,0xba2cb9f9,0x3af1baf8,0xbaf1baf8,0xba2c39f9,0xba84ba5b,0x3adcbae7,0xbadcbae7,0xba843a5b,
  0xbaacba98,0x3abebace,0xbabebace,0xbaac3a98,0xbaf5baff,0xba153949,0x3a153949,0xbaf53aff,0xbac6bae2,0xbaa23a71,0x3aa23a71,0xbac63ae2,
  0xba71baa2,0xbae23ac6,0x3ae23ac6,0xba713aa2,0xb949ba15,0xbaff3af5,0x3aff3af5,0xb9493a15,0x3a5b3996,0xbae73afd,0x3ae73afd,0x3a5bb996,
  0x3adc3aac,0xba843abe,0x3a843abe,0x3adcbaac,0x3b003af8,0x38c939f9,0xb8c939f9,0x3b00baf8,0x3ace3af1,0x3a98ba2c,0xba98ba2c,0x3acebaf1,
  0x3ad53afb,0x3a8eb9c8,0xba8eb9c8,0x3ad5bafb,0x39c83a8e,0x3afbbad5,0xbafbbad5,0x39c8ba8e,0xba8eb9c8,0x3ad5bafb,0xbad5bafb,0xba8e39c8,
  0xbafbbad5,0x39c8ba8e,0xb9c8ba8e,0xbafb3ad5,0xbaacb9f9,0x3abebaf8,0xbabebaf8,0xbaac39f9,0xbafdbaf1,0xb996ba2c,0x3996ba2c,0xbafd3af1,
  0xba5bbace,0xbae73a98,0x3ae73a98,0xba5b3ace,0x3a8438c9,0xbadc3b00,0x3adc3b00,0x3a84b8c9,0xbaa2baf5,0xbac63a15,0x3ac63a15,0xbaa23af5,
  0x3a71b949,0xbae23aff,0x3ae23aff,0x3a713949,0x3aff3ae2,0x39493a71,0xb9493a71,0x3affbae2,0x3a153ac6,0x3af5baa2,0xbaf5baa2,0x3a15bac6,
  0x3adc3a2c,0xba843af1,0x3a843af1,0x3adcba2c,0x3aac3afd,0x3abeb996,0xbabeb996,0x3aacbafd,0xba9838c9,0x3acebb00,0xbacebb00,0xba98b8c9,
  0xbae7baf8,0xba5bb9f9,0x3a5bb9f9,0xbae73af8,0x3a443aed,0x3aedba44,0xbaedba44,0x3a44baed,0xbaedba44,0x3a44baed,0xba44baed,0xbaed3a44,
  0xba44baed,0xbaed3a44,0x3aed3a44,0xba443aed,0x3aed3a44,0xba443aed,0x3a443aed,0x3aedba44,0xbaf8ba5b,0x39f9bae7,0xb9f9bae7,0xbaf83a5b,
  0xb8c9bace,0xbb003a98,0x3b003a98,0xb8c93ace,0x3afd3abe,0x39963aac,0xb9963aac,0x3afdbabe,0xba2c3a84,0x3af1badc,0xbaf1badc,0xba2cba84,
  0xb949bae2,0xbaff3a71,0x3aff3a71,0xb9493ae2,0x3af53ac6,0x3a153aa2,0xba153aa2,0x3af5bac6,0xbaa23a15,0x3ac6baf5,0xbac6baf5,0xbaa2ba15,
  0xba71baff,0xbae23949,0x3ae23949,0xba713aff,0x3b003a84,0x38c93adc,0xb8c93adc,0x3b00ba84,0xba983a5b,0x3acebae7,0xbacebae7,0xba98ba5b,
  0xba2cbafd,0xbaf13996,0x3af13996,0xba2c3afd,0x3af83aac,0x39f93abe,0xb9f93abe,0x3af8baac,0xb9c83ad5,0x3afbba8e,0xbafbba8e,0xb9c8bad5,
  0xba8ebafb,0xbad5b9c8,0x3ad5b9c8,0xba8e3afb,0x3afb3a8e,0x39c83ad5,0xb9c83ad5,0x3afbba8e,0xbad539c8,0x3a8ebafb,0xba8ebafb,0xbad5b9c8,
  0xbaf1ba98,0xba2cbace,0x3a2cbace,0xbaf13a98,0x3af838c9,0xb9f93b00,0x39f93b00,0x3af8b8c9,0xbaac3a84,0x3abebadc,0xbabebadc,0xbaacba84,
  0x3996bae7,0xbafd3a5b,0x3afd3a5b,0x39963ae7,0x3a71bac6,0xbae23aa2,0x3ae23aa2,0x3a713ac6,0xb9493af5,0x3affba15,0xbaffba15,0xb949baf5,
  0xba15baff,0xbaf5b949,0x3af5b949,0xba153aff,0x3aa23ae2,0x3ac63a71,0xbac63a71,0x3aa2bae2,0x3ace3aac,0x3a983abe,0xba983abe,0x3acebaac,
  0xbae7ba84,0xba5bbadc,0x3a5bbadc,0xbae73a84,0x3af83a2c,0x39f93af1,0xb9f93af1,0x3af8ba2c,0xbb00b996,0xb8c9bafd,0x38c9bafd,0xbb003996,
  0xbab53ab5,0x3ab5bab5,0xbab5bab5,0xbab5bab5,0x3ab5bab5,0xbab53ab5,0x3ab53ab5,0x3ab53ab5,0xbab53ab5,0x3ab5bab5,0xbab5bab5,0xbab5bab5,
  0x3ab5bab5,0xbab53ab5,0x3ab53ab5,0x3ab53ab5,0xba98babe,0xbacebaac,0x3acebaac,0xba983abe,0x3a5b3adc,0x3ae73a84,0xbae73a84,0x3a5bbadc,
  0xb9f9baf1,0xbaf8ba2c,0x3af8ba2c,0xb9f93af1,0x38c93afd,0x3b003996,0xbb003996,0x38c9bafd,0x3ae2baa2,0xba713ac6,0x3a713ac6,0x3ae23aa2,
  0xbaff3a15,0x3949baf5,0xb949baf5,0xbaffba15,0x3af53949,0x3a153aff,0xba153aff,0x3af5b949,0xbac6ba71,0xbaa2bae2,0x3aa2bae2,0xbac63a71,
  0x3a2c3ace,0x3af13a98,0xbaf13a98,0x3a2cbace,0x39f9bb00,0xbaf8b8c9,0x3af8b8c9,0x39f93b00,0xbabe3adc,0x3aacba84,0xbaacba84,0xbabebadc,
  0x3afdba5b,0xb9963ae7,0x39963ae7,0x3afd3a5b,0xbafb3a8e,0x39c8bad5,0xb9c8bad5,0xbafbba8e,0x3ad539c8,0x3a8e3afb,0xba8e3afb,0x3ad5b9c8,
  0xb9c8bad5,0xbafbba8e,0x3afbba8e,0xb9c83ad5,0xba8e3afb,0x3ad5b9c8,0xbad5b9c8,0xba8ebafb,0xb8c9badc,0xbb00ba84,0x3b00ba84,0xb8c93adc,
  0xbace3ae7,0x3a98ba5b,0xba98ba5b,0xbacebae7,0x3af1b996,0x3a2c3afd,0xba2c3afd,0x3af13996,0xb9f9babe,0xbaf8baac,0x3af8baac,0xb9f93abe,
  0x3affba71,0x39493ae2,0xb9493ae2,0x3aff3a71,0xba15baa2,0xbaf5bac6,0x3af5bac6,0xba153aa2,0xbac63af5,0x3aa2ba15,0xbaa2ba15,0xbac6baf5,
  0x3ae2b949,0x3a713aff,0xba713aff,0x3ae23949,0xb9f93ae7,0x3af83a5b,0xbaf83a5b,0xb9f9bae7,0x3b00ba98,0x38c93ace,0xb8c93ace,0x3b003a98,
  0xb996baac,0xbafdbabe,0x3afdbabe,0xb9963aac,0xbaf13adc,0x3a2cba84,0xba2cba84,0xbaf1badc,0xbaed3a44,0xba44baed,0x3a44baed,0xbaedba44,
  0xba443aed,0x3aed3a44,0xbaed3a44,0xba44baed,0x3aedba44,0x3a443aed,0xba443aed,0x3aed3a44,0x3a44baed,0xbaedba44,0x3aedba44,0x3a443aed,
  0x3a84baf1,0xbadcba2c,0x3adcba2c,0x3a843af1,0xbabe3996,0xbaacbafd,0x3aacbafd,0xbabeb996,0xbace3b00,0x3a98b8c9,0xba98b8c9,0xbacebb00,
  0x3a5b39f9,0x3ae73af8,0xbae73af8,0x3a5bb9f9,0x3ac6ba15,0x3aa23af5,0xbaa23af5,0x3ac63a15,0x3ae2baff,0xba713949,0x3a713949,0x3ae23aff,
  0xb949ba71,0xbaffbae2,0x3affbae2,0xb9493a71,0xbaf53aa2,0xba15bac6,0x3a15bac6,0xbaf5baa2,0xbabe3af8,0x3aac39f9,0xbaac39f9,0xbabebaf8,
  0x39963a2c,0x3afd3af1,0xbafd3af1,0x3996ba2c,0x3ae7ba98,0x3a5b3ace,0xba5b3ace,0x3ae73a98,0x3adcbb00,0xba84b8c9,0x3a84b8c9,0x3adc3b00,
  0xba8e39c8,0xbad5bafb,0x3ad5bafb,0xba8eb9c8,0xbafb3ad5,0xb9c8ba8e,0x39c8ba8e,0xbafbbad5,0xbad53afb,0x3a8e39c8,0xba8e39c8,0xbad5bafb,
  0xb9c83a8e,0x3afb3ad5,0xbafb3ad5,0xb9c8ba8e,0x3ae7bafd,0xba5bb996,0x3a5bb996,0x3ae73afd,0x3a84babe,0xbadcbaac,0x3adcbaac,0x3a843abe,
  0xb8c9b9f9,0xbb00baf8,0x3b00baf8,0xb8c939f9,0xba983a2c,0xbacebaf1,0x3acebaf1,0xba98ba2c,0x3a15b949,0x3af53aff,0xbaf53aff,0x3a153949,
  0x3aa2ba71,0x3ac63ae2,0xbac63ae2,0x3aa23a71,0x3ae2bac6,0x3a713aa2,0xba713aa2,0x3ae23ac6,0x3affbaf5,0x39493a15,0xb9493a15,0x3aff3af5,
  0xbafd3b00,0x399638c9,0xb99638c9,0xbafdbb00,0xbaf13af8,0x3a2c39f9,0xba2c39f9,0xbaf1baf8,0xbadc3ae7,0x3a843a5b,0xba843a5b,0xbadcbae7,
  0xbabe3ace,0x3aac3a98,0xbaac3a98,0xbabebace,0x3b003b00,0x00000000,0x80008000,0x3b00bb00,0x3b003b00,0x00000000,0x80008000,0x3b00bb00,
  0x3b003b00,0x00000000,0x80008000,0x3b00bb00,0x3b003b00,0x00000000,0x80008000,0x3b00bb00,0xbacebabe,0x3a98baac,0xba98baac,0xbace3abe,
  0xbae7badc,0x3a5bba84,0xba5bba84,0xbae73adc,0xbaf8baf1,0x39f9ba2c,0xb9f9ba2c,0xbaf83af1,0xbb00bafd,0x38c9b996,0xb8c9b996,0xbb003afd,
  0x3a153949,0xbaf53aff,0x3af53aff,0x3a15b949,0x3aa23a71,0xbac63ae2,0x3ac63ae2,0x3aa2ba71,0x3ae23ac6,0xba713aa2,0x3a713aa2,0x3ae2bac6,
  0x3aff3af5,0xb9493a15,0x39493a15,0x3affbaf5,0x3a2c3a98,0x3af1bace,0xbaf1bace,0x3a2cba98,0xb9f938c9,0x3af8bb00,0xbaf8bb00,0xb9f9b8c9,
  0xbabeba84,0x3aacbadc,0xbaacbadc,0xbabe3a84,0xbafdbae7,0x3996ba5b,0xb996ba5b,0xbafd3ae7,0xbad5bafb,0xba8e39c8,0x3a8e39c8,0xbad53afb,
  0xb9c8ba8e,0xbafb3ad5,0x3afb3ad5,0xb9c83a8e,0x3a8e39c8,0xbad53afb,0x3ad53afb,0x3a8eb9c8,0x3afb3ad5,0xb9c83a8e,0x39c83a8e,0x3afbbad5,
  0x3b003adc,0xb8c93a84,0x38c93a84,0x3b00badc,0x3a983ae7,0x3aceba5b,0xbaceba5b,0x3a98bae7,0xba2c3996,0x3af1bafd,0xbaf1bafd,0xba2cb996,
  0xbaf8babe,0x39f9baac,0xb9f9baac,0xbaf83abe,0xbac6ba15,0x3aa2baf5,0xbaa2baf5,0xbac63a15,0xbae2baff,0xba71b949,0x3a71b949,0xbae23aff,
  0x3949ba71,0xbaff3ae2,0x3aff3ae2,0x39493a71,0x3af53aa2,0xba153ac6,0x3a153ac6,0x3af5baa2,0x39f9ba5b,0xbaf83ae7,0x3af83ae7,0x39f93a5b,
  0x3b003ace,0x38c93a98,0xb8c93a98,0x3b00bace,0x39963abe,0x3afdbaac,0xbafdbaac,0x3996babe,0xbaf1ba84,0x3a2cbadc,0xba2cbadc,0xbaf13a84,
  0x3a443aed,0x3aedba44,0xbaedba44,0x3a44baed,0xbaedba44,0x3a44baed,0xba44baed,0xbaed3a44,0xba44baed,0xbaed3a44,0x3aed3a44,0xba443aed,
  0x3aed3a44,0xba443aed,0x3a443aed,0x3aedba44,0xbadcbaf1,0xba84ba2c,0x3a84ba2c,0xbadc3af1,0x3aacb996,0xbabe3afd,0x3abe3afd,0x3aac3996,
  0x3a983b00,0x3aceb8c9,0xbaceb8c9,0x3a98bb00,0xbae7b9f9,0x3a5bbaf8,0xba5bbaf8,0xbae739f9,0x3aff3a71,0xb9493ae2,0x39493ae2,0x3affba71,
  0xba153aa2,0x3af5bac6,0xbaf5bac6,0xba15baa2,0xbac6baf5,0xbaa2ba15,0x3aa2ba15,0xbac63af5,0x3ae23949,0xba713aff,0x3a713aff,0x3ae2b949,
  0xbabe39f9,0x3aacbaf8,0xbaacbaf8,0xbabeb9f9,0xb996baf1,0xbafd3a2c,0x3afd3a2c,0xb9963af1,0x3ae73ace,0x3a5b3a98,0xba5b3a98,0x3ae7bace,
  0xbadc38c9,0x3a84bb00,0xba84bb00,0xbadcb8c9,0x39c8bad5,0xbafb3a8e,0x3afb3a8e,0x39c83ad5,0x3a8e3afb,0x3ad539c8,0xbad539c8,0x3a8ebafb,
  0xbafbba8e,0xb9c8bad5,0x39c8bad5,0xbafb3a8e,0x3ad5b9c8,0xba8e3afb,0x3a8e3afb,0x3ad539c8,0x3a5b3afd,0x3ae73996,0xbae73996,0x3a5bbafd,
  0xbadcbabe,0xba84baac,0x3a84baac,0xbadc3abe,0x3b0039f9,0xb8c93af8,0x38c93af8,0x3b00b9f9,0xbace3a2c,0x3a98baf1,0xba98baf1,0xbaceba2c,
  0xbae2baa2,0xba71bac6,0x3a71bac6,0xbae23aa2,0x3aff3a15,0x39493af5,0xb9493af5,0x3affba15,0xbaf53949,0x3a15baff,0xba15baff,0xbaf5b949,
  0x3ac6ba71,0xbaa23ae2,0x3aa23ae2,0x3ac63a71,0x3afdb8c9,0xb9963b00,0x39963b00,0x3afd38c9,0xbaf139f9,0x3a2cbaf8,0xba2cbaf8,0xbaf1b9f9,
  0x3adcba5b,0xba843ae7,0x3a843ae7,0x3adc3a5b,0xbabe3a98,0x3aacbace,0xbaacbace,0xbabeba98,0xbab53ab5,0x3ab5bab5,0xbab5bab5,0xbab5bab5,
  0x3ab5bab5,0xbab53ab5,0x3ab53ab5,0x3ab53ab5,0xbab53ab5,0x3ab5bab5,0xbab5bab5,0xbab5bab5,0x3ab5bab5,0xbab53ab5,0x3ab53ab5,0x3ab53ab5,
  0x3996bb00,0xbafd38c9,0x3afd38c9,0x39963b00,0xba2c3af8,0x3af1b9f9,0xbaf1b9f9,0xba2cbaf8,0x3a84bae7,0xbadc3a5b,0x3adc3a5b,0x3a843ae7,
  0xbaac3ace,0x3abeba98,0xbabeba98,0xbaacbace,0x3a713ac6,0x3ae23aa2,0xbae23aa2,0x3a71bac6,0xb949baf5,0xbaffba15,0x3affba15,0xb9493af5,
  0xba153aff,0x3af5b949,0xbaf5b949,0xba15baff,0x3aa2bae2,0xbac63a71,0x3ac63a71,0x3aa23ae2,0xbae7b996,0xba5bbafd,0x3a5bbafd,0xbae73996,
  0x3a843aac,0x3adc3abe,0xbadc3abe,0x3a84baac,0x38c9baf8,0xbb00b9f9,0x3b00b9f9,0x38c93af8,0xba983af1,0x3aceba2c,0xbaceba2c,0xba98baf1,
  0x3afbba8e,0xb9c83ad5,0x39c83ad5,0x3afb3a8e,0xbad5b9c8,0xba8ebafb,0x3a8ebafb,0xbad539c8,0x39c83ad5,0x3afb3a8e,0xbafb3a8e,0x39c8bad5,
  0x3a8ebafb,0xbad539c8,0x3ad539c8,0x3a8e3afb,0xbaac3af8,0x3abeb9f9,0xbabeb9f9,0xbaacbaf8,0x3afdba2c,0x39963af1,0xb9963af1,0x3afd3a2c,
  0xba5bba98,0xbae7bace,0x3ae7bace,0xba5b3a98,0xba843b00,0x3adcb8c9,0xbadcb8c9,0xba84bb00,0x3949bae2,0xbaffba71,0x3affba71,0x39493ae2,
  0xbaf53ac6,0x3a15baa2,0xba15baa2,0xbaf5bac6,0x3aa23a15,0x3ac63af5,0xbac63af5,0x3aa2ba15,0x3a71baff,0xbae2b949,0x3ae2b949,0x3a713aff,
  0x3a843a2c,0x3adc3af1,0xbadc3af1,0x3a84ba2c,0x3abebafd,0xbaac3996,0x3aac3996,0x3abe3afd,0xbace38c9,0xba98bb00,0x3a98bb00,0xbaceb8c9,
  0xba5b3af8,0x3ae739f9,0xbae739f9,0xba5bbaf8,0xbaed3a44,0xba44baed,0x3a44baed,0xbaedba44,0xba443aed,0x3aed3a44,0xbaed3a44,0xba44baed,
  0x3aedba44,0x3a443aed,0xba443aed,0x3aed3a44,0x3a44baed,0xbaedba44,0x3aedba44,0x3a443aed,0x3af8bae7,0xb9f93a5b,0x39f93a5b,0x3af83ae7,
  0xb8c9ba98,0xbb00bace,0x3b00bace,0xb8c93a98,0xbafd3aac,0xb996babe,0x3996babe,0xbafdbaac,0xba2c3adc,0x3af13a84,0xbaf13a84,0xba2cbadc,
  0xbaa23af5,0x3ac63a15,0xbac63a15,0xbaa2baf5,0x3a713949,0x3ae23aff,0xbae23aff,0x3a71b949,0x3affbae2,0xb9493a71,0x39493a71,0x3aff3ae2,
  0x3a15bac6,0xbaf5baa2,0x3af5baa2,0x3a153ac6,0x38c9ba84,0xbb00badc,0x3b00badc,0x38c93a84,0xbace3a5b,0xba98bae7,0x3a98bae7,0xbaceba5b,
  0xbaf13afd,0x3a2cb996,0xba2cb996,0xbaf1bafd,0xb9f93aac,0x3af83abe,0xbaf83abe,0xb9f9baac,0x3a8eb9c8,0x3ad53afb,0xbad53afb,0x3a8e39c8,
  0x3afbbad5,0x39c83a8e,0xb9c83a8e,0x3afb3ad5,0x3ad5bafb,0xba8eb9c8,0x3a8eb9c8,0x3ad53afb,0x39c8ba8e,0xbafbbad5,0x3afbbad5,0x39c83a8e,
  0xbaf13ace,0xba2cba98,0x3a2cba98,0xbaf1bace,0xbaf83b00,0x39f9b8c9,0xb9f9b8c9,0xbaf8bb00,0xbaac3adc,0x3abe3a84,0xbabe3a84,0xbaacbadc,
  0xb9963a5b,0x3afd3ae7,0xbafd3ae7,0xb996ba5b,0x3af5baff,0xba15b949,0x3a15b949,0x3af53aff,0x3ac6bae2,0xbaa2ba71,0x3aa2ba71,0x3ac63ae2,
  0x3a71baa2,0xbae2bac6,0x3ae2bac6,0x3a713aa2,0x3949ba15,0xbaffbaf5,0x3affbaf5,0x39493a15,0xba983aac,0x3ace3abe,0xbace3abe,0xba98baac,
  0xba5b3a84,0x3ae73adc,0xbae73adc,0xba5bba84,0xb9f93a2c,0x3af83af1,0xbaf83af1,0xb9f9ba2c,0xb8c93996,0x3b003afd,0xbb003afd,0xb8c9b996,
  0x3f800000,0x3f7fffb1,0x3f7fec43,0x3f7fe705,0x3f7ffec4,0x3f7ffd39,0x3f7fe129,0x3f7fdaaf,0x3f7ffb11,0x3f7ff84a,0x3f7fd397,0x3f7fcbe2,
  0x3f7ff4e6,0x3f7ff0e3,0x3f7fc38f,0x3f7fba9e,0x3f800000,0x3f7ffd39,0x3f7f4e6d,0x3f7f1f49,0x3f7ff4e6,0x3f7fe705,0x3f7eea9d,0x3f7eb069,
  0x3f7fd397,0x3f7fba9e,0x3f7e70b0,0x3f7e2b72,0x3f7f9c18,0x3f7f7808,0x3f7de0b1,0x3f7d906e,0x3f800000,0x3f7ff84a,0x3f7e1324,0x3f7d906e,
  0x3f7fe129,0x3f7fba9e,0x3f7cfe73,0x3f7c5d3a,0x3f7f84ab,0x3f7f3f54,0x3f7baccd,0x3f7aed37,0x3f7eea9d,0x3f7e868b,0x3f7a1e84,0x3f7940c0,
  0x3f800000,0x3f7ff0e3,0x3f7c3b28,0x3f7b3bab,0x3f7fc38f,0x3f7f7808,0x3f7a1e84,0x3f78e3d6,0x3f7f0e58,0x3f7e868b,0x3f778bc5,0x3f76167a,
  0x3f7de0b1,0x3f7d1cdd,0x3f748422,0x3f72d4eb,0x3f800000,0x3f7fe705,0x3f79c79d,0x3f7822d1,0x3f7f9c18,0x3f7f1f49,0x3f764d97,0x3f74484b,
  0x3f7e70b0,0x3f7d906e,0x3f721352,0x3f6faf1b,0x3f7c7eb0,0x3f7b3bab,0x3f6d1c1d,0x3f6a5ad9,0x3f800000,0x3f7fdaaf,0x3f76ba07,0x3f74484b,
  0x3f7f6ac7,0x3f7eb069,0x3f718f57,0x3f6e8ff8,0x3f7dabcc,0x3f7c5d3a,0x3f6b4b0c,0x3f67c187,0x3f7ac516,0x3f78e3d6,0x3f63f473,0x3f5fe4e9,
  0x3f800000,0x3f7fcbe2,0x3f731447,0x3f6faf1b,0x3f7f2f9d,0x3f7e2b72,0x3f6be858,0x3f67c187,0x3f7cbfc9,0x3f7aed37,0x3f633c5a,0x3f5e5aa6,
  0x3f78b47b,0x3f76167a,0x3f591e6a,0x3f5389c7,0x3f800000,0x3f7fba9e,0x3f6ed89e,0x3f6a5ad9,0x3f7eea9d,0x3f7d906e,0x3f655e0b,0x3f5fe4e9,
  0x3f7baccd,0x3f7940c0,0x3f59f26a,0x3f5389c7,0x3f764d97,0x3f72d4eb,0x3f4cae79,0x3f456439,0x3f800000,0x3f7fa6e3,0x3f6a09a7,0x3f644fac,
  0x3f7e9bc9,0x3f7cdf6c,0x3f5df6be,0x3f570348,0x3f7a7302,0x3f77583a,0x3f4f7a1f,0x3f476085,0x3f73913f,0x3f6f20b0,0x3f3ebc1b,0x3f3592e7,
  0x3f800000,0x3f7f90b1,0x3f64aa59,0x3f5d924d,0x3f7e4323,0x3f7c187a,0x3f55b993,0x3f4d26fd,0x3f791298,0x3f75341d,0x3f43e200,0x3f39f2ac,
  0x3f708066,0x3f6afb8c,0x3f2f61a5,0x3f24381a,0x3f800000,0x3f7f7808,0x3f5ebe05,0x3f5627fe,0x3f7de0b1,0x3f7b3bab,0x3f4cae79,0x3f425b89,
  0x3f778bc5,0x3f72d4eb,0x3f373a23,0x3f2b561b,0x3f6d1c1d,0x3f666771,0x3f1ebc12,0x3f11796b,0x3f800000,0x3f7f5ce9,0x3f584853,0x3f4e1689,
  0x3f7d7474,0x3f7a4910,0x3f42de29,0x3f36ad7f,0x3f75dec6,0x3f703b37,0x3f299415,0x3f1ba299,0x3f696591,0x3f61668a,0x3f0cead0,0x3efafef7,
  0x3f800000,0x3f7f3f54,0x3f514d3d,0x3f456439,0x3f7cfe73,0x3f7940c0,0x3f385216,0x3f2a2a80,0x3f740bdd,0x3f6d67a1,0x3f1b02c6,0x3f0af1b7,
  0x3f655e0b,0x3f5bfb34,0x3ef41f07,0x3ed0eb2a,0x3f800000,0x3f7f1f49,0x3f49d112,0x3f3c17d9,0x3f7c7eb0,0x3f7822d1,0x3f2d1469,0x3f1ce11f,
  0x3f721352,0x3f6a5ad9,0x3f0b9a6b,0x3ef2bd43,0x3f6106f2,0x3f5627fe,0x3ecc9b8b,0x3ea5129f,0x3f800000,0x3f7efcc9,0x3f41d870,0x3f3238aa,
  0x3f7bf531,0x3f76ef5b,0x3f212ff9,0x3f0ee0db,0x3f6ff573,0x3f671599,0x3ef6e0cb,0x3ece0bea,0x3f5c61c7,0x3f4fefa8,0x3ea395c5,0x3e6fa8b2,
  0x3f800000,0x3f7ed7d4,0x3f396842,0x3f27ce61,0x3f7b61fc,0x3f75a67b,0x3f14b039,0x3f003a06,0x3f6db293,0x3f6398ac,0x3ed53641,0x3ea80b1f,
  0x3f577026,0x3f495521,0x3e72b651,0x3e1324ca,0x3f800000,0x3f7eb069,0x3f3085bb,0x3f1ce11f,0x3f7ac516,0x3f74484b,0x3f07a136,0x3ee1fb6a,
  0x3f6b4b0c,0x3f5fe4e9,0x3eb263ef,0x3e80f8c0,0x3f5233c6,0x3f425b89,0x3e1c76de,0x3d55880e,0x3f800000,0x3f7e868b,0x3f273656,0x3f11796b,
  0x3f7a1e84,0x3f72d4eb,0x3ef41f07,0x3ec27b55,0x3f68bf3c,0x3f5bfb34,0x3e8e9a22,0x3e3228d4,0x3f4cae79,0x3f3b0629,0x3d8a200a,0xbd2351cb,
  0x3f800000,0x3f7e5a38,0x3f1d7fd1,0x3f05a02c,0x3f796e4e,0x3f714c7a,0x3ed8106b,0x3ea21887,0x3f660f88,0x3f57dc7f,0x3e541501,0x3dc27c39,
  0x3f46e22a,0x3f33587a,0xbc96c9b6,0xbe06b26e,0x3f800000,0x3f7e2b72,0x3f13682a,0x3ef2bd43,0x3f78b47b,0x3f6faf1b,0x3ebb31a0,0x3e80f8c0,
  0x3f633c5a,0x3f5389c7,0x3e09cf86,0x3c7b514b,0x3f40d0da,0x3f2b561b,0xbdd53db9,0xbe636c83,0x3f800000,0x3f7dfa38,0x3f08f59b,0x3ed97cb9,
  0x3f77f110,0x3f6dfcf2,0x3e9d9e78,0x3e3e853e,0x3f604621,0x3f4f0417,0x3d7b2b74,0xbd83db0a,0x3f3a7ca4,0x3f2302d3,0xbe419b37,0xbe9f1cdf,
  0x3f800000,0x3f7dc68c,0x3efc5d27,0x3ebf926f,0x3f772417,0x3f6c3624,0x3e7ee6e1,0x3df475c0,0x3f5d2d53,0x3f4a4c87,0xbc490e90,0xbe1324ca,
  0x3f33e7bc,0x3f1a6293,0xbe8b9507,0xbecb2aae,0x3f800000,0x3f7d906e,0x3ee63375,0x3ea5129f,0x3f764d97,0x3f6a5ad9,0x3e419b37,0x3d55880e,
  0x3f59f26a,0x3f456439,0xbdafb680,0xbe636c83,0x3f2d1469,0x3f11796b,0xbeb554ec,0xbef58035,0x3f800000,0x3f7d57de,0x3ecf7bca,0x3e8a11f7,
  0x3f756d97,0x3f686b39,0x3e039502,0xbc7b514b,0x3f5695e5,0x3f404c5c,0xbe22abb6,0xbe9920fe,0x3f26050a,0x3f084b92,0xbeddbe79,0xbf0ee0db,
  0x3f800000,0x3f7d1cdd,0x3eb8442a,0x3e5d4b1a,0x3f748422,0x3f666771,0x3d8a200a,0xbda973ba,0x3f531849,0x3f3b0629,0xbe6c9a7f,0xbebf926f,
  0x3f1ebc12,0x3efdbabb,0xbf0242b1,0xbf21cbfb,0x3f800000,0x3f7cdf6c,0x3ea09ae5,0x3e25c58c,0x3f73913f,0x3f644fac,0x3bc90f88,0xbe195be0,
  0x3f4f7a1f,0x3f3592e7,0xbe9aa086,0xbee4cbfe,0x3f173c07,0x3eea6681,0xbf14b039,0xbf33587a,0x3f800000,0x3f7c9f8a,0x3e888e93,0x3ddb7d37,
  0x3f7294f8,0x3f62241a,0xbd621469,0xbe5d4b1a,0x3f4bbbf8,0x3f2ff3e6,0xbebe1d4a,0xbf044889,0x3f0f8784,0x3ed6a399,0xbf26050a,0xbf436051,
  0x3f800000,0x3f7c5d3a,0x3e605c13,0x3d55880e,0x3f718f57,0x3f5fe4e9,0xbdee3876,0xbe901c2c,0x3f47de65,0x3f2a2a80,0xbee0924f,0xbf1553b7,
  0x3f07a136,0x3ec27b55,0xbf36206c,0xbf51c0c2,0x3f800000,0x3f7c187a,0x3e2f10a2,0xbb490fc6,0x3f708066,0x3f5d924d,0xbe354098,0xbeb0eacb,
  0x3f43e200,0x3f24381a,0xbf00e7e4,0xbf256bcb,0x3eff17b2,0x3eadf73c,0xbf44e3f5,0xbf5e5aa6,0x3f800000,0x3f7bd14d,0x3dfab273,0xbd6ea038,
  0x3f6f6830,0x3f5b2c79,0xbe72b651,0xbed0eb2a,0x3f3fc767,0x3f1e1e22,0xbf10d3cd,0xbf34768f,0x3eee9479,0x3e9920fe,0xbf5233c6,0xbf6912ae,
  0x3f800000,0x3f7b87b2,0x3d96a905,0xbde7fa9a,0x3f6e46be,0x3f58b3a1,0xbe97a117,0xbeeff7fb,0x3f3b8f3b,0x3f17de12,0xbf1ff6cb,0xbf425b89,
  0x3eddbe79,0x3e840270,0xbf5df6be,0xbf71d19f,0x3f800000,0x3f7b3bab,0x3cc90ab0,0xbe2bf804,0x3f6d1c1d,0x3f5627fe,0xbeb554ec,0xbf06f686,
  0x3f373a23,0x3f11796b,0xbf2e3bde,0xbf4f0417,0x3ecc9b8b,0x3e5d4b1a,0xbf6816a8,0xbf788486,0x80000000,0xbb490fc6,0xbcc90ab0,0xbce22a7a,
  0xbbc90f88,0xbc16cb58,0xbcfb49ba,0xbd0a342f,0xbc490e90,0xbc7b514b,0xbd16c32c,0xbd2351cb,0xbc96c9b6,0xbcafea69,0xbd2fe007,0xbd3c6dd5,
  0x80000000,0xbc16cb58,0xbd96a905,0xbda973ba,0xbc96c9b6,0xbce22a7a,0xbdbc3ac3,0xbdcefdb7,0xbd16c32c,0xbd3c6dd5,0xbde1bc2e,0xbdf475c0,
  0xbd621469,0xbd83db0a,0xbe039502,0xbe0cec4a,0x80000000,0xbc7b514b,0xbdfab273,0xbe0cec4a,0xbcfb49ba,0xbd3c6dd5,0xbe1c76de,0xbe2bf804,
  0xbd7b2b74,0xbd9cecf9,0xbe3b6ecf,0xbe4ada4f,0xbdbc3ac3,0xbddb7d37,0xbe5a3997,0xbe698bba,0x80000000,0xbcafea69,0xbe2f10a2,0xbe44b0b9,
  0xbd2fe007,0xbd83db0a,0xbe5a3997,0xbe6fa8b2,0xbdafb680,0xbddb7d37,0xbe827dc0,0xbe8d17c0,0xbe039502,0xbe195be0,0xbe97a117,0xbea21887,
  0x80000000,0xbce22a7a,0xbe605c13,0xbe7bdba4,0xbd621469,0xbda973ba,0xbe8b9507,0xbe9920fe,0xbde1bc2e,0xbe0cec4a,0xbea68f12,0xbeb3dca5,
  0xbe28defc,0xbe44b0b9,0xbec1071e,0xbece0bea,0x80000000,0xbd0a342f,0xbe888e93,0xbe9920fe,0xbd8a200a,0xbdcefdb7,0xbea986c4,0xbeb9bb1e,
  0xbe09cf86,0xbe2bf804,0xbec9b953,0xbed97cb9,0xbe4dee60,0xbe6fa8b2,0xbee900b7,0xbef840c8,0x80000000,0xbd2351cb,0xbea09ae5,0xbeb3dca5,
  0xbda3308c,0xbdf475c0,0xbec6d529,0xbed97cb9,0xbe22abb6,0xbe4ada4f,0xbeebcbbb,0xbefdbabb,0xbe72b651,0xbe8d17c0,0xbf07a136,0xbf102dd5,
  0x80000000,0xbd3c6dd5,0xbeb8442a,0xbece0bea,0xbdbc3ac3,0xbe0cec4a,0xbee363fa,0xbef840c8,0xbe3b6ecf,0xbe698bba,0xbf064b82,0xbf102dd5,
  0xbe8b9507,0xbea21887,0xbf19c200,0xbf2302d3,0x80000000,0xbd55880e,0xbecf7bca,0xbee79a5d,0xbdd53db9,0xbe1f917b,0xbeff17b2,0xbf0af1b7,
  0xbe541501,0xbe840270,0xbf15f6d9,0xbf209393,0xbe9d9e78,0xbeb6ccc3,0xbf2ac082,0xbf34768f,0x80000000,0xbd6ea038,0xbee63375,0xbf003a06,
  0xbdee3876,0xbe3228d4,0xbf0cead0,0xbf19210f,0xbe6c9a7f,0xbe931f35,0xbf24d225,0xbf2ff3e6,0xbeaf713a,0xbecb2aae,0xbf3a7ca4,0xbf446337,
  0x80000000,0xbd83db0a,0xbefc5d27,0xbf0c42c9,0xbe039502,0xbe44b0b9,0xbf19c200,0xbf269de3,0xbe827dc0,0xbea21887,0xbf32c8c9,0xbf3e35c5,
  0xbec1071e,0xbedf28a9,0xbf48d8b3,0xbf52a649,0x80000000,0xbd9064b4,0xbf08f59b,0xbf17de12,0xbe1008b7,0xbe57278f,0xbf26050a,0xbf33587a,
  0xbe8e9a22,0xbeb0eacb,0xbf3fc767,0xbf4b41fa,0xbed25a09,0xbef2bd43,0xbf55b993,0xbf5f20db,0x80000000,0xbd9cecf9,0xbf13682a,0xbf2302d3,
  0xbe1c76de,0xbe698bba,0xbf31a81d,0xbf3f41fc,0xbe9aa086,0xbebf926f,0xbf4bbbf8,0xbf570348,0xbee363fa,0xbf02ef9f,0xbf6106f2,0xbf69b7e4,
  0x80000000,0xbda973ba,0xbf1d7fd1,0xbf2da859,0xbe28defc,0xbe7bdba4,0xbf3ca003,0xbf4a4c87,0xbea68f12,0xbece0bea,0xbf5695e5,0xbf61668a,
  0xbef41f07,0xbf0c42c9,0xbf6aab7b,0xbf725470,0x80000000,0xbdb5f8da,0xbf273656,0xbf37c655,0xbe354098,0xbe870ada,0xbf46e22a,0xbf546b3b,
  0xbeb263ef,0xbedc53c1,0xbf604621,0xbf6a5ad9,0xbf0242b1,0xbf1553b7,0xbf7294f8,0xbf78e3d6,0x80000000,0xbdc27c39,0xbf3085bb,0xbf4154e1,
  0xbe419b37,0xbe901c2c,0xbf5064af,0xbf5d924d,0xbebe1d4a,0xbeea6681,0xbf68bf3c,0xbf71d19f,0xbf0a48ad,0xbf1e1e22,0xbf78b47b,0xbf7d57de,
  0x80000000,0xbdcefdb7,0xbf396842,0xbf4a4c87,0xbe4dee60,0xbe9920fe,0xbf591e6a,0xbf65b710,0xbec9b953,0xbef840c8,0xbf6ff573,0xbf77beb7,
  0xbf121eb0,0xbf269de3,0xbf7cfe73,0xbf7fa6e3,0x80000000,0xbddb7d37,0xbf41d870,0xbf52a649,0xbe5a3997,0xbea21887,0xbf6106f2,0xbf6cd007,
  0xbed53641,0xbf02ef9f,0xbf75dec6,0xbf7c187a,0xbf19c200,0xbf2ecef7,0xbf7f6ac7,0xbf7fcbe2,0x80000000,0xbde7fa9a,0xbf49d112,0xbf5a5ba0,
  0xbe667c66,0xbeab0201,0xbf6816a8,0xbf72d4eb,0xbee0924f,0xbf099f4e,0xbf7a7302,0xbf7ed7d4,0xbf212ff9,0xbf36ad7f,0xbf7ff4e6,0xbf7dc68c,
  0x80000000,0xbdf475c0,0xbf514d3d,0xbf61668a,0xbe72b651,0xbeb3dca5,0xbf6e46be,0xbf77beb7,0xbeebcbbb,0xbf102dd5,0xbf7dabcc,0xbf7ff84a,
  0xbf286605,0xbf3e35c5,0xbf7e9bc9,0xbf799b43,0x80000000,0xbe007745,0xbf584853,0xbf67c187,0xbe7ee6e1,0xbebca7af,0xbf73913f,0xbf7b87b2,
  0xbef6e0cb,0xbf16999f,0xbf7f84ab,0xbf7f7808,0xbf2f61a5,0xbf456439,0xbf7b61fc,0xbf73530e,0x80000000,0xbe06b26e,0xbf5ebe05,0xbf6d67a1,
  0xbe8586ce,0xbec5625c,0xbf77f110,0xbf7e2b72,0xbf00e7e4,0xbf1ce11f,0xbf7ffb11,0xbf7d57de,0xbf36206c,0xbf4c3578,0xbf764d97,0xbf6afb8c,
  0x80000000,0xbe0cec4a,0xbf64aa59,0xbf725470,0xbe8b9507,0xbece0bea,0xbf7b61fc,0xbf7fa6e3,0xbf064b82,0xbf2302d3,0xbf7f0e58,0xbf799b43,
  0xbf3ca003,0xbf52a649,0xbf6f6830,0xbf60a6cf,0x80000000,0xbe1324ca,0xbf6a09a7,0xbf76841b,0xbe919ddd,0xbed6a399,0xbf7de0b1,0xbf7ff84a,
  0xbf0b9a6b,0xbf28fd41,0xbf7cbfc9,0xbf74484b,0xbf42de29,0xbf58b3a1,0xbf66becc,0xbf546b3b,0x80000000,0xbe195be0,0xbf6ed89e,0xbf79f35e,
  0xbe97a117,0xbedf28a9,0xbf7f6ac7,0xbf7f1f49,0xbf10d3cd,0xbf2ecef7,0xbf791298,0xbf6d67a1,0xbf48d8b3,0xbf5e5aa6,0xbf5c61c7,0xbf466354,
  0x80000000,0xbe1f917b,0xbf731447,0xbf7c9f8a,0xbe9d9e78,0xbee79a5d,0xbf7ffec4,0xbf7d1cdd,0xbf15f6d9,0xbf34768f,0xbf740bdd,0xbf650479,
  0xbf4e8d90,0xbf6398ac,0xbf5064af,0xbf36ad7f,0x80000000,0xbe25c58c,0xbf76ba07,0xbf7e868b,0xbea395c5,0xbeeff7fb,0xbf7f9c18,0xbf79f35e,
  0xbf1b02c6,0xbf39f2ac,0xbf6db293,0xbf5b2c79,0xbf53fac3,0xbf686b39,0xbf42de29,0xbf256bcb,0x80000000,0xbe2bf804,0xbf79c79d,0xbf7fa6e3,
  0xbea986c4,0xbef840c8,0xbf7e4323,0xbf75a67b,0xbf1ff6cb,0xbf3f41fc,0xbf660f88,0xbf4fefa8,0xbf591e6a,0xbf6cd007,0xbf33e7bc,0xbf12c39a,
  0x80000000,0xbe3228d4,0xbf7c3b28,0xbf7fffb1,0xbeaf713a,0xbf003a06,0xbf7bf531,0xbf703b37,0xbf24d225,0xbf446337,0xbf5d2d53,0xbf436051,
  0xbf5df6be,0xbf70c501,0xbf239da9,0xbefdbabb,0x80000000,0xbe3857ec,0xbf7e1324,0xbf7f90b1,0xbeb554ec,0xbf044889,0xbf78b47b,0xbf69b7e4,
  0xbf299415,0xbf495521,0xbf531849,0xbf3592e7,0xbf628210,0xbf74484b,0xbf121eb0,0xbed3c867,0x80000000,0xbe3e853e,0xbf7f4e6d,0xbf7e5a38,
  0xbebb31a0,0xbf084b92,0xbf748422,0xbf62241a,0xbf2e3bde,0xbf4e1689,0xbf47de65,0xbf269de3,0xbf66becc,0xbf77583a,0xbeff17b2,0xbea80b1f,
  0x80000000,0xbe44b0b9,0xbf7fec43,0xbf7c5d3a,0xbec1071e,0xbf0c42c9,0xbf6f6830,0xbf5988ad,0xbf32c8c9,0xbf52a649,0xbf3b8f3b,0xbf16999f,
  0xbf6aab7b,0xbf79f35e,0xbed8106b,0xbe75c35a,
};
__device__ __align__(128) const uint32_t c_img[1536] = {
  0x3f803f80,0x3f803f80,0x3f803f80,0x3f803f80,0x3f803f80,0x3f803f80,0x3f803f80,0x3f803f80,0x3f803f80,0x3f803f80,0x3f803f80,0x3f803f80,
  0x3f803f80,0x3f803f80,0x3f803f80,0x3f803f80,0x3f803f80,0x3f803f80,0x3f803f80,0x3f803f80,0x3f803f80,0x3f803f80,0x3f803f80,0x3f803f80,
  0x3f803f80,0x3f803f80,0x3f803f80,0x3f803f80,0x3f803f80,0x3f803f80,0x3f803f80,0x3f803f80,0x3f803f80,0x3f803f80,0x3f803f80,0x3f803f80,
  0x3f803f80,0x3f803f80,0x3f803f80,0x3f803f80,0x3f803f80,0x3f803f80,0x3f803f80,0x3f803f80,0x3f803f80,0x3f803f80,0x3f803f80,0x3f803f80,
  0x3f803f80,0x3f803f80,0x3f803f80,0x3f803f80,0x3f803f80,0x3f803f80,0x3f803f80,0x3f803f80,0x3f803f80,0x3f803f80,0x3f803f80,0x3f803f80,
  0x3f803f80,0x3f803f80,0x3f803f80,0x3f803f80,0x3f803f80,0x3f803f80,0x3f803f80,0x3f803f80,0x3f803f80,0x3f803f80,0x3f803f80,0x3f803f80,
  0x3f803f80,0x3f803f80,0x3f803f80,0x3f803f80,0x3f803f80,0x3f803f80,0x3f803f80,0x3f803f80,0x3f803f80,0x3f803f80,0x3f803f80,0x3f803f80,
  0x3f803f80,0x3f803f80,0x3f803f80,0x3f803f80,0x3f803f80,0x3f803f80,0x3f803f80,0x3f803f80,0x3f803f80,0x3f803f80,0x3f803f80,0x3f803f80,
  0x3f803f80,0x3f803f80,0x3f803f80,0x3f803f80,0x3f803f80,0x3f803f80,0x3f803f80,0x3f803f80,0x3f803f80,0x3f803f80,0x3f803f80,0x3f803f80,
  0x3f803f80,0x3f803f80,0x3f803f80,0x3f803f80,0x3f803f80,0x3f803f80,0x3f803f80,0x3f803f80,0x3f803f80,0x3f803f80,0x3f803f80,0x3f803f80,
  0x3f803f80,0x3f803f80,0x3f803f80,0x3f803f80,0x3f803f80,0x3f803f80,0x3f803f80,0x3f803f80,0x3f803f80,0x3f803f80,0x3f803f80,0x3f803f80,
  0x3f803f80,0x3f803f80,0x3f803f80,0x3f803f80,0x3f803f80,0x3f803f80,0x3f803f80,0x3f803f80,0x3f803f80,0x3f803f80,0x3f803f80,0x3f803f80,
  0x3f803f80,0x3f803f80,0x3f803f80,0x3f803f80,0x3f803f80,0x3f803f80,0x3f803f80,0x3f803f80,0x3f803f80,0x3f803f80,0x3f803f80,0x3f803f80,
  0x3f803f80,0x3f803f80,0x3f803f80,0x3f803f80,0x3f803f80,0x3f803f80,0x3f803f80,0x3f803f80,0x3f803f80,0x3f803f80,0x3f803f80,0x3f803f80,
  0x3f803f80,0x3f803f80,0x3f803f80,0x3f803f80,0x3f803f80,0x3f803f80,0x3f803f80,0x3f803f80,0x3f803f80,0x3f803f80,0x3f803f80,0x3f803f80,
  0x3f803f80,0x3f803f80,0x3f803f80,0x3f803f80,0x3f803f80,0x3f803f80,0x3f803f80,0x3f803f80,0x3f803f80,0x3f803f80,0x3f803f80,0x3f803f80,
  0x3f803f80,0x3f803f80,0x3f803f80,0x3f803f80,0x3f803f80,0x3f803f80,0x3f803f80,0x3f803f80,0x3f803f80,0x3f803f80,0x3f803f80,0x3f803f80,
  0x3f803f80,0x3f803f80,0x3f803f80,0x3f803f80,0x3f803f80,0x3f803f80,0x3f803f80,0x3f803f80,0x3f803f80,0x3f803f80,0x3f803f80,0x3f803f80,
  0x3f803f80,0x3f803f80,0x3f803f80,0x3f803f80,0x3f803f80,0x3f803f80,0x3f803f80,0x3f803f80,0x3f803f80,0x3f803f80,0x3f803f80,0x3f803f80,
  0x3f803f80,0x3f803f80,0x3f803f80,0x3f803f80,0x3f803f80,0x3f803f80,0x3f803f80,0x3f803f80,0x3f803f80,0x3f803f80,0x3f803f80,0x3f803f80,
  0x3f803f80,0x3f803f80,0x3f803f80,0x3f803f80,0x3f803f80,0x3f803f80,0x3f803f80,0x3f803f80,0x3f803f80,0x3f803f80,0x3f803f80,0x3f803f80,
  0x3f803f80,0x3f803f80,0x3f803f80,0x3f803f80,0x3f803f80,0x3f803f80,0x3f803f80,0x3f803f80,0x3f803f80,0x3f803f80,0x3f803f80,0x3f803f80,
  0x3f803f80,0x3f803f80,0x3f803f80,0x3f803f80,0x3f803f80,0x3f803f80,0x3f803f80,0x3f803f80,0x3f803f80,0x3f803f80,0x3f803f80,0x3f803f80,
  0x3f803f80,0x3f803f80,0x3f803f80,0x3f803f80,0x3f803f80,0x3f803f80,0x3f803f80,0x3f803f80,0x3f803f80,0x3f803f80,0x3f803f80,0x3f803f80,
  0x3f803f80,0x3f803f80,0x3f803f80,0x3f803f80,0x3f803f80,0x3f803f80,0x3f803f80,0x3f803f80,0x3f803f80,0x3f803f80,0x3f803f80,0x3f803f80,
  0x3f803f80,0x3f803f80,0x3f803f80,0x3f803f80,0x3f803f80,0x3f803f80,0x3f803f80,0x3f803f80,0x3f803f80,0x3f803f80,0x3f803f80,0x3f803f80,
  0x3f803f80,0x3f803f80,0x3f803f80,0x3f803f80,0x3f803f80,0x3f803f80,0x3f803f80,0x3f803f80,0x3f803f80,0x3f803f80,0x3f803f80,0x3f803f80,
  0x3f803f80,0x3f803f80,0x3f803f80,0x3f803f80,0x3f803f80,0x3f803f80,0x3f803f80,0x3f803f80,0x3f803f80,0x3f803f80,0x3f803f80,0x3f803f80,
  0x3f803f80,0x3f803f80,0x3f803f80,0x3f803f80,0x3f803f80,0x3f803f80,0x3f803f80,0x3f803f80,0x3f803f80,0x3f803f80,0x3f803f80,0x3f803f80,
  0x3f803f80,0x3f803f80,0x3f803f80,0x3f803f80,0x3f803f80,0x3f803f80,0x3f803f80,0x3f803f80,0x3f803f80,0x3f803f80,0x3f803f80,0x3f803f80,
  0x3f803f80,0x3f803f80,0x3f803f80,0x3f803f80,0x3f803f80,0x3f803f80,0x3f803f80,0x3f803f80,0x3f803f80,0x3f803f80,0x3f803f80,0x3f803f80,
  0x3f803f80,0x3f803f80,0x3f803f80,0x3f803f80,0x3f803f80,0x3f803f80,0x3f803f80,0x3f803f80,0x3f803f80,0x3f803f80,0x3f803f80,0x3f803f80,
  0x3f803f80,0x3f803f80,0x3f803f80,0x3f803f80,0x3f803f80,0x3f803f80,0x3f803f80,0x3f803f80,0x3f803f80,0x3f803f80,0x3f803f80,0x3f803f80,
  0x3f803f80,0x3f803f80,0x3f803f80,0x3f803f80,0x3f803f80,0x3f803f80,0x3f803f80,0x3f803f80,0x3f803f80,0x3f803f80,0x3f803f80,0x3f803f80,
  0x3f803f80,0x3f803f80,0x3f803f80,0x3f803f80,0x3f803f80,0x3f803f80,0x3f803f80,0x3f803f80,0x3f803f80,0x3f803f80,0x3f803f80,0x3f803f80,
  0x3f803f80,0x3f803f80,0x3f803f80,0x3f803f80,0x3f803f80,0x3f803f80,0x3f803f80,0x3f803f80,0x3f803f80,0x3f803f80,0x3f803f80,0x3f803f80,
  0x3f803f80,0x3f803f80,0x3f803f80,0x3f803f80,0x3f803f80,0x3f803f80,0x3f803f80,0x3f803f80,0x3f803f80,0x3f803f80,0x3f803f80,0x3f803f80,
  0x3f803f80,0x3f803f80,0x3f803f80,0x3f803f80,0x3f803f80,0x3f803f80,0x3f803f80,0x3f803f80,0x3f803f80,0x3f803f80,0x3f803f80,0x3f803f80,
  0x3f803f80,0x3f803f80,0x3f803f80,0x3f803f80,0x3f803f80,0x3f803f80,0x3f803f80,0x3f803f80,0x3f803f80,0x3f803f80,0x3f803f80,0x3f803f80,
  0x3f803f80,0x3f803f80,0x3f803f80,0x3f803f80,0x3f803f80,0x3f803f80,0x3f803f80,0x3f803f80,0x3f803f80,0x3f803f80,0x3f803f80,0x3f803f80,
  0x3f803f80,0x3f803f80,0x3f803f80,0x3f803f80,0x3f803f80,0x3f803f80,0x3f803f80,0x3f803f80,0x3f803f80,0x3f803f80,0x3f803f80,0x3f803f80,
  0x3f803f80,0x3f803f80,0x3f803f80,0x3f803f80,0x3f803f80,0x3f803f80,0x3f803f80,0x3f803f80,0x3f803f80,0x3f803f80,0x3f803f80,0x3f803f80,
  0x3f803f80,0x3f803f80,0x3f803f80,0x3f803f80,0x3f803f80,0x3f803f80,0x3f803f80,0x3f803f80,0x3f803f80,0x3f803f80,0x3f803f80,0x3f803f80,
  0x3f6d3f80,0x3ec43f35,0xbec40000,0xbf6dbf35,0x3f353f80,0xbf350000,0xbf35bf80,0x3f350000,0x3ec43f80,0xbf6dbf35,0x3f6d0000,0xbec43f35,
  0x00003f80,0x0000bf80,0x00003f80,0x0000bf80,0xbec43f80,0x3f6dbf35,0xbf6d0000,0x3ec43f35,0xbf353f80,0x3f350000,0x3f35bf80,0xbf350000,
  0xbf6d3f80,0xbec43f35,0x3ec40000,0x3f6dbf35,0x3f803f80,0x3f803f80,0x3f803f80,0x3f803f80,0xbf6dbf80,0xbec4bf35,0x3ec40000,0x3f6d3f35,
  0x3f353f80,0xbf350000,0xbf35bf80,0x3f350000,0xbec4bf80,0x3f6d3f35,0xbf6d0000,0x3ec4bf35,0x00003f80,0x0000bf80,0x00003f80,0x0000bf80,
  0x3ec4bf80,0xbf6d3f35,0x3f6d0000,0xbec4bf35,0xbf353f80,0x3f350000,0x3f35bf80,0xbf350000,0x3f6dbf80,0x3ec4bf35,0xbec40000,0xbf6d3f35,
  0x00000000,0x00000000,0x00000000,0x00000000,0x3ec40000,0x3f6d3f35,0x3f6d3f80,0x3ec43f35,0x3f350000,0x3f353f80,0xbf350000,0xbf35bf80,
  0x3f6d0000,0xbec43f35,0xbec4bf80,0x3f6d3f35,0x3f800000,0xbf800000,0x3f800000,0xbf800000,0x3f6d0000,0xbec4bf35,0xbec43f80,0x3f6dbf35,
  0x3f350000,0x3f35bf80,0xbf350000,0xbf353f80,0x3ec40000,0x3f6dbf35,0x3f6dbf80,0x3ec4bf35,0x00000000,0x00000000,0x00000000,0x00000000,
  0xbec40000,0xbf6dbf35,0xbf6dbf80,0xbec4bf35,0x3f350000,0x3f353f80,0xbf350000,0xbf35bf80,0xbf6d0000,0x3ec4bf35,0x3ec43f80,0xbf6dbf35,
  0x3f800000,0xbf800000,0x3f800000,0xbf800000,0xbf6d0000,0x3ec43f35,0x3ec4bf80,0xbf6d3f35,0x3f350000,0x3f35bf80,0xbf350000,0xbf353f80,
  0xbec40000,0xbf6d3f35,0xbf6d3f80,0xbec43f35,0xbf803f80,0xbf803f80,0xbf803f80,0xbf803f80,0xbf6d3f80,0xbec43f35,0x3ec40000,0x3f6dbf35,
  0xbf353f80,0x3f350000,0x3f35bf80,0xbf350000,0xbec43f80,0x3f6dbf35,0xbf6d0000,0x3ec43f35,0x00003f80,0x0000bf80,0x00003f80,0x0000bf80,
  0x3ec43f80,0xbf6dbf35,0x3f6d0000,0xbec43f35,0x3f353f80,0xbf350000,0xbf35bf80,0x3f350000,0x3f6d3f80,0x3ec43f35,0xbec40000,0xbf6dbf35,
  0xbf803f80,0xbf803f80,0xbf803f80,0xbf803f80,0x3f6dbf80,0x3ec4bf35,0xbec40000,0xbf6d3f35,0xbf353f80,0x3f350000,0x3f35bf80,0xbf350000,
  0x3ec4bf80,0xbf6d3f35,0x3f6d0000,0xbec4bf35,0x00003f80,0x0000bf80,0x00003f80,0x0000bf80,0xbec4bf80,0x3f6d3f35,0xbf6d0000,0x3ec4bf35,
  0x3f353f80,0xbf350000,0xbf35bf80,0x3f350000,0xbf6dbf80,0xbec4bf35,0x3ec40000,0x3f6d3f35,0x00000000,0x00000000,0x00000000,0x00000000,
  0xbec40000,0xbf6d3f35,0xbf6d3f80,0xbec43f35,0xbf350000,0xbf353f80,0x3f350000,0x3f35bf80,0xbf6d0000,0x3ec43f35,0x3ec4bf80,0xbf6d3f35,
  0xbf800000,0x3f800000,0xbf800000,0x3f800000,0xbf6d0000,0x3ec4bf35,0x3ec43f80,0xbf6dbf35,0xbf350000,0xbf35bf80,0x3f350000,0x3f353f80,
  0xbec40000,0xbf6dbf35,0xbf6dbf80,0xbec4bf35,0x00000000,0x00000000,0x00000000,0x00000000,0x3ec40000,0x3f6dbf35,0x3f6dbf80,0x3ec4bf35,
  0xbf350000,0xbf353f80,0x3f350000,0x3f35bf80,0x3f6d0000,0xbec4bf35,0xbec43f80,0x3f6dbf35,0xbf800000,0x3f800000,0xbf800000,0x3f800000,
  0x3f6d0000,0xbec43f35,0xbec4bf80,0x3f6d3f35,0xbf350000,0xbf35bf80,0x3f350000,0x3f353f80,0x3ec40000,0x3f6d3f35,0x3f6d3f80,0x3ec43f35,
  0x80008000,0x80008000,0x80008000,0x80008000,0xbec48000,0xbf6dbf35,0xbf6dbf80,0xbec4bf35,0xbf358000,0xbf35bf80,0x3f358000,0x3f353f80,
  0xbf6d8000,0x3ec4bf35,0x3ec43f80,0xbf6dbf35,0xbf808000,0x3f808000,0xbf808000,0x3f808000,0xbf6d8000,0x3ec43f35,0x3ec4bf80,0xbf6d3f35,
  0xbf358000,0xbf353f80,0x3f358000,0x3f35bf80,0xbec48000,0xbf6d3f35,0xbf6d3f80,0xbec43f35,0x80008000,0x80008000,0x80008000,0x80008000,
  0x3ec48000,0x3f6d3f35,0x3f6d3f80,0x3ec43f35,0xbf358000,0xbf35bf80,0x3f358000,0x3f353f80,0x3f6d8000,0xbec43f35,0xbec4bf80,0x3f6d3f35,
  0xbf808000,0x3f808000,0xbf808000,0x3f808000,0x3f6d8000,0xbec4bf35,0xbec43f80,0x3f6dbf35,0xbf358000,0xbf353f80,0x3f358000,0x3f35bf80,
  0x3ec48000,0x3f6dbf35,0x3f6dbf80,0x3ec4bf35,0x3f803f80,0x3f803f80,0x3f803f80,0x3f803f80,0x3f6d3f80,0x3ec43f35,0xbec40000,0xbf6dbf35,
  0x3f353f80,0xbf350000,0xbf35bf80,0x3f350000,0x3ec43f80,0xbf6dbf35,0x3f6d0000,0xbec43f35,0x00003f80,0x0000bf80,0x00003f80,0x0000bf80,
  0xbec43f80,0x3f6dbf35,0xbf6d0000,0x3ec43f35,0xbf353f80,0x3f350000,0x3f35bf80,0xbf350000,0xbf6d3f80,0xbec43f35,0x3ec40000,0x3f6dbf35,
  0x3f803f80,0x3f803f80,0x3f803f80,0x3f803f80,0xbf6dbf80,0xbec4bf35,0x3ec40000,0x3f6d3f35,0x3f353f80,0xbf350000,0xbf35bf80,0x3f350000,
  0xbec4bf80,0x3f6d3f35,0xbf6d0000,0x3ec4bf35,0x00003f80,0x0000bf80,0x00003f80,0x0000bf80,0x3ec4bf80,0xbf6d3f35,0x3f6d0000,0xbec4bf35,
  0xbf353f80,0x3f350000,0x3f35bf80,0xbf350000,0x3f6dbf80,0x3ec4bf35,0xbec40000,0xbf6d3f35,0x80008000,0x80008000,0x80008000,0x80008000,
  0x3ec48000,0x3f6dbf35,0x3f6dbf80,0x3ec4bf35,0x3f358000,0x3f35bf80,0xbf358000,0xbf353f80,0x3f6d8000,0xbec4bf35,0xbec43f80,0x3f6dbf35,
  0x3f808000,0xbf808000,0x3f808000,0xbf808000,0x3f6d8000,0xbec43f35,0xbec4bf80,0x3f6d3f35,0x3f358000,0x3f353f80,0xbf358000,0xbf35bf80,
  0x3ec48000,0x3f6d3f35,0x3f6d3f80,0x3ec43f35,0x80008000,0x80008000,0x80008000,0x80008000,0xbec48000,0xbf6d3f35,0xbf6d3f80,0xbec43f35,
  0x3f358000,0x3f35bf80,0xbf358000,0xbf353f80,0xbf6d8000,0x3ec43f35,0x3ec4bf80,0xbf6d3f35,0x3f808000,0xbf808000,0x3f808000,0xbf808000,
  0xbf6d8000,0x3ec4bf35,0x3ec43f80,0xbf6dbf35,0x3f358000,0x3f353f80,0xbf358000,0xbf35bf80,0xbec48000,0xbf6dbf35,0xbf6dbf80,0xbec4bf35,
  0xbf803f80,0xbf803f80,0xbf803f80,0xbf803f80,0xbf6d3f80,0xbec43f35,0x3ec40000,0x3f6dbf35,0xbf353f80,0x3f350000,0x3f35bf80,0xbf350000,
  0xbec43f80,0x3f6dbf35,0xbf6d0000,0x3ec43f35,0x00003f80,0x0000bf80,0x00003f80,0x0000bf80,0x3ec43f80,0xbf6dbf35,0x3f6d0000,0xbec43f35,
  0x3f353f80,0xbf350000,0xbf35bf80,0x3f350000,0x3f6d3f80,0x3ec43f35,0xbec40000,0xbf6dbf35,0xbf803f80,0xbf803f80,0xbf803f80,0xbf803f80,
  0x3f6dbf80,0x3ec4bf35,0xbec40000,0xbf6d3f35,0xbf353f80,0x3f350000,0x3f35bf80,0xbf350000,0x3ec4bf80,0xbf6d3f35,0x3f6d0000,0xbec4bf35,
  0x00003f80,0x0000bf80,0x00003f80,0x0000bf80,0xbec4bf80,0x3f6d3f35,0xbf6d0000,0x3ec4bf35,0x3f353f80,0xbf350000,0xbf35bf80,0x3f350000,
  0xbf6dbf80,0xbec4bf35,0x3ec40000,0x3f6d3f35,0x3f803f80,0x3f803f80,0x3f803f80,0x3f803f80,0x3f6d3f80,0x3ec43f35,0xbec40000,0xbf6dbf35,
  0x3f353f80,0xbf350000,0xbf35bf80,0x3f350000,0x3ec43f80,0xbf6dbf35,0x3f6d0000,0xbec43f35,0x00003f80,0x0000bf80,0x00003f80,0x0000bf80,
  0xbec43f80,0x3f6dbf35,0xbf6d0000,0x3ec43f35,0xbf353f80,0x3f350000,0x3f35bf80,0xbf350000,0xbf6d3f80,0xbec43f35,0x3ec40000,0x3f6dbf35,
  0x3f803f80,0x3f803f80,0x3f803f80,0x3f803f80,0xbf6dbf80,0xbec4bf35,0x3ec40000,0x3f6d3f35,0x3f353f80,0xbf350000,0xbf35bf80,0x3f350000,
  0xbec4bf80,0x3f6d3f35,0xbf6d0000,0x3ec4bf35,0x00003f80,0x0000bf80,0x00003f80,0x0000bf80,0x3ec4bf80,0xbf6d3f35,0x3f6d0000,0xbec4bf35,
  0xbf353f80,0x3f350000,0x3f35bf80,0xbf350000,0x3f6dbf80,0x3ec4bf35,0xbec40000,0xbf6d3f35,0x80008000,0x80008000,0x80008000,0x80008000,
  0xbec48000,0xbf6dbf35,0xbf6dbf80,0xbec4bf35,0xbf358000,0xbf35bf80,0x3f358000,0x3f353f80,0xbf6d8000,0x3ec4bf35,0x3ec43f80,0xbf6dbf35,
  0xbf808000,0x3f808000,0xbf808000,0x3f808000,0xbf6d8000,0x3ec43f35,0x3ec4bf80,0xbf6d3f35,0xbf358000,0xbf353f80,0x3f358000,0x3f35bf80,
  0xbec48000,0xbf6d3f35,0xbf6d3f80,0xbec43f35,0x80008000,0x80008000,0x80008000,0x80008000,0x3ec48000,0x3f6d3f35,0x3f6d3f80,0x3ec43f35,
  0xbf358000,0xbf35bf80,0x3f358000,0x3f353f80,0x3f6d8000,0xbec43f35,0xbec4bf80,0x3f6d3f35,0xbf808000,0x3f808000,0xbf808000,0x3f808000,
  0x3f6d8000,0xbec4bf35,0xbec43f80,0x3f6dbf35,0xbf358000,0xbf353f80,0x3f358000,0x3f35bf80,0x3ec48000,0x3f6dbf35,0x3f6dbf80,0x3ec4bf35,
  0xbf803f80,0xbf803f80,0xbf803f80,0xbf803f80,0xbf6d3f80,0xbec43f35,0x3ec40000,0x3f6dbf35,0xbf353f80,0x3f350000,0x3f35bf80,0xbf350000,
  0xbec43f80,0x3f6dbf35,0xbf6d0000,0x3ec43f35,0x00003f80,0x0000bf80,0x00003f80,0x0000bf80,0x3ec43f80,0xbf6dbf35,0x3f6d0000,0xbec43f35,
  0x3f353f80,0xbf350000,0xbf35bf80,0x3f350000,0x3f6d3f80,0x3ec43f35,0xbec40000,0xbf6dbf35,0xbf803f80,0xbf803f80,0xbf803f80,0xbf803f80,
  0x3f6dbf80,0x3ec4bf35,0xbec40000,0xbf6d3f35,0xbf353f80,0x3f350000,0x3f35bf80,0xbf350000,0x3ec4bf80,0xbf6d3f35,0x3f6d0000,0xbec4bf35,
  0x00003f80,0x0000bf80,0x00003f80,0x0000bf80,0xbec4bf80,0x3f6d3f35,0xbf6d0000,0x3ec4bf35,0x3f353f80,0xbf350000,0xbf35bf80,0x3f350000,
  0xbf6dbf80,0xbec4bf35,0x3ec40000,0x3f6d3f35,0x80008000,0x80008000,0x80008000,0x80008000,0x3ec48000,0x3f6dbf35,0x3f6dbf80,0x3ec4bf35,
  0x3f358000,0x3f35bf80,0xbf358000,0xbf353f80,0x3f6d8000,0xbec4bf35,0xbec43f80,0x3f6dbf35,0x3f808000,0xbf808000,0x3f808000,0xbf808000,
  0x3f6d8000,0xbec43f35,0xbec4bf80,0x3f6d3f35,0x3f358000,0x3f353f80,0xbf358000,0xbf35bf80,0x3ec48000,0x3f6d3f35,0x3f6d3f80,0x3ec43f35,
  0x80008000,0x80008000,0x80008000,0x80008000,0xbec48000,0xbf6d3f35,0xbf6d3f80,0xbec43f35,0x3f358000,0x3f35bf80,0xbf358000,0xbf353f80,
  0xbf6d8000,0x3ec43f35,0x3ec4bf80,0xbf6d3f35,0x3f808000,0xbf808000,0x3f808000,0xbf808000,0xbf6d8000,0x3ec4bf35,0x3ec43f80,0xbf6dbf35,
  0x3f358000,0x3f353f80,0xbf358000,0xbf35bf80,0xbec48000,0xbf6dbf35,0xbf6dbf80,0xbec4bf35,0x00000000,0x00000000,0x00000000,0x00000000,
  0x3ec40000,0x3f6d3f35,0x3f6d3f80,0x3ec43f35,0x3f350000,0x3f353f80,0xbf350000,0xbf35bf80,0x3f6d0000,0xbec43f35,0xbec4bf80,0x3f6d3f35,
  0x3f800000,0xbf800000,0x3f800000,0xbf800000,0x3f6d0000,0xbec4bf35,0xbec43f80,0x3f6dbf35,0x3f350000,0x3f35bf80,0xbf350000,0xbf353f80,
  0x3ec40000,0x3f6dbf35,0x3f6dbf80,0x3ec4bf35,0x00000000,0x00000000,0x00000000,0x00000000,0xbec40000,0xbf6dbf35,0xbf6dbf80,0xbec4bf35,
  0x3f350000,0x3f353f80,0xbf350000,0xbf35bf80,0xbf6d0000,0x3ec4bf35,0x3ec43f80,0xbf6dbf35,0x3f800000,0xbf800000,0x3f800000,0xbf800000,
  0xbf6d0000,0x3ec43f35,0x3ec4bf80,0xbf6d3f35,0x3f350000,0x3f35bf80,0xbf350000,0xbf353f80,0xbec40000,0xbf6d3f35,0xbf6d3f80,0xbec43f35,
  0x3f803f80,0x3f803f80,0x3f803f80,0x3f803f80,0x3f6d3f80,0x3ec43f35,0xbec40000,0xbf6dbf35,0x3f353f80,0xbf350000,0xbf35bf80,0x3f350000,
  0x3ec43f80,0xbf6dbf35,0x3f6d0000,0xbec43f35,0x00003f80,0x0000bf80,0x00003f80,0x0000bf80,0xbec43f80,0x3f6dbf35,0xbf6d0000,0x3ec43f35,
  0xbf353f80,0x3f350000,0x3f35bf80,0xbf350000,0xbf6d3f80,0xbec43f35,0x3ec40000,0x3f6dbf35,0x3f803f80,0x3f803f80,0x3f803f80,0x3f803f80,
  0xbf6dbf80,0xbec4bf35,0x3ec40000,0x3f6d3f35,0x3f353f80,0xbf350000,0xbf35bf80,0x3f350000,0xbec4bf80,0x3f6d3f35,0xbf6d0000,0x3ec4bf35,
  0x00003f80,0x0000bf80,0x00003f80,0x0000bf80,0x3ec4bf80,0xbf6d3f35,0x3f6d0000,0xbec4bf35,0xbf353f80,0x3f350000,0x3f35bf80,0xbf350000,
  0x3f6dbf80,0x3ec4bf35,0xbec40000,0xbf6d3f35,0x00000000,0x00000000,0x00000000,0x00000000,0xbec40000,0xbf6d3f35,0xbf6d3f80,0xbec43f35,
  0xbf350000,0xbf353f80,0x3f350000,0x3f35bf80,0xbf6d0000,0x3ec43f35,0x3ec4bf80,0xbf6d3f35,0xbf800000,0x3f800000,0xbf800000,0x3f800000,
  0xbf6d0000,0x3ec4bf35,0x3ec43f80,0xbf6dbf35,0xbf350000,0xbf35bf80,0x3f350000,0x3f353f80,0xbec40000,0xbf6dbf35,0xbf6dbf80,0xbec4bf35,
  0x00000000,0x00000000,0x00000000,0x00000000,0x3ec40000,0x3f6dbf35,0x3f6dbf80,0x3ec4bf35,0xbf350000,0xbf353f80,0x3f350000,0x3f35bf80,
  0x3f6d0000,0xbec4bf35,0xbec43f80,0x3f6dbf35,0xbf800000,0x3f800000,0xbf800000,0x3f800000,0x3f6d0000,0xbec43f35,0xbec4bf80,0x3f6d3f35,
  0xbf350000,0xbf35bf80,0x3f350000,0x3f353f80,0x3ec40000,0x3f6d3f35,0x3f6d3f80,0x3ec43f35,0xbf803f80,0xbf803f80,0xbf803f80,0xbf803f80,
  0xbf6d3f80,0xbec43f35,0x3ec40000,0x3f6dbf35,0xbf353f80,0x3f350000,0x3f35bf80,0xbf350000,0xbec43f80,0x3f6dbf35,0xbf6d0000,0x3ec43f35,
  0x00003f80,0x0000bf80,0x00003f80,0x0000bf80,0x3ec43f80,0xbf6dbf35,0x3f6d0000,0xbec43f35,0x3f353f80,0xbf350000,0xbf35bf80,0x3f350000,
  0x3f6d3f80,0x3ec43f35,0xbec40000,0xbf6dbf35,0xbf803f80,0xbf803f80,0xbf803f80,0xbf803f80,0x3f6dbf80,0x3ec4bf35,0xbec40000,0xbf6d3f35,
  0xbf353f80,0x3f350000,0x3f35bf80,0xbf350000,0x3ec4bf80,0xbf6d3f35,0x3f6d0000,0xbec4bf35,0x00003f80,0x0000bf80,0x00003f80,0x0000bf80,
  0xbec4bf80,0x3f6d3f35,0xbf6d0000,0x3ec4bf35,0x3f353f80,0xbf350000,0xbf35bf80,0x3f350000,0xbf6dbf80,0xbec4bf35,0x3ec40000,0x3f6d3f35,
};

__device__ __align__(128) float    g_kv[2][16][2176];
__device__ __align__(128) uint4    g_o[16 * 16 * 1024];
__device__ __align__(128) unsigned g_kvcnt[16 * 32];
__device__ __align__(128) unsigned g_ocnt[16 * 32];
__device__ unsigned g_epoch[128];
#define GSTAMP(role, i) do {} while (0)
#define STAMP(role, i) do {} while (0)

constexpr int STAGE_BYTES = 57344;
constexpr int OFF_PK = 0, OFF_V = 114688, OFF_H = 4 * 16384, OFF_VP = 9 * 16384;
constexpr int OFF_XT = 172032, XT_STRIDE = 4112;
constexpr int OFF_ONES = 205824, OFF_F2F = 207872, OFF_F2I = 209920, OFF_KVB = 211968;
constexpr int OFF_STG = 217088, STG_STRIDE = 4224, OFF_BAR = 229760, SMEM_TOTAL = 230400;
enum { B_FULL1 = 0, B_EMPTY1 = 3, B_H = 6, B_XT = 8, B_KV = 9, B_Y = 10, B_PKFREE = 11, B_HFREE = 12, B_VFREE = 14,
       B_STG = 15, B_ODONE = 21, B_FULL2 = 24, B_CONS2 = 40, B_COUNT = 56 };
constexpr uint64_t SLOT_A = 0x5649256492564954ull;
constexpr uint64_t SLOT_B = 0x7103871038710326ull;
constexpr int SPIN_LIMIT = 1 << 22;

__device__ __forceinline__ uint32_t smem_u32(const void* p) { return (uint32_t)__cvta_generic_to_shared(p); }
__device__ __forceinline__ void wg_fence() { asm volatile("wgmma.fence.sync.aligned;" ::: "memory"); }
__device__ __forceinline__ void wg_commit() { asm volatile("wgmma.commit_group.sync.aligned;" ::: "memory"); }
template <int N> __device__ __forceinline__ void wg_wait() { asm volatile("wgmma.wait_group.sync.aligned %0;" ::"n"(N) : "memory"); }
template <int N> __device__ __forceinline__ void keep(float (&d)[N]) {
#pragma unroll
  for (int i = 0; i < N; i++) asm volatile("" : "+f"(d[i])::"memory");
}
__device__ __forceinline__ uint64_t mkdesc(uint32_t addr, uint32_t lbo, uint32_t sbo, uint32_t swz) {
  uint32_t lo = ((addr & 0x3FFFF) >> 4) | ((lbo >> 4) << 16), hi = (sbo >> 4) | (swz << 30);
  return ((uint64_t)hi << 32) | lo;
}
__device__ __forceinline__ void mbar_init(uint32_t bar, int cnt) { asm volatile("mbarrier.init.shared::cta.b64 [%0], %1;" ::"r"(bar), "r"(cnt)); }
__device__ __forceinline__ void mbar_expect(uint32_t bar, int bytes) { asm volatile("mbarrier.arrive.expect_tx.shared::cta.b64 _, [%0], %1;" ::"r"(bar), "r"(bytes) : "memory"); }
__device__ __forceinline__ void mbar_arrive(uint32_t bar) { asm volatile("mbarrier.arrive.shared::cta.b64 _, [%0];" ::"r"(bar) : "memory"); }
__device__ __forceinline__ void mbar_arrive_cl(uint32_t bar, uint32_t cta) {
  asm volatile("{\n.reg .b32 r;\nmapa.shared::cluster.u32 r, %0, %1;\nmbarrier.arrive.shared::cluster.b64 _, [r];\n}\n" ::"r"(bar), "r"(cta) : "memory");
}
__device__ __forceinline__ void mbar_wait(uint32_t bar, uint32_t parity) {
  asm volatile("{\n.reg .pred p;\n.reg .u32 n;\nmov.u32 n, 0;\n"
               "W_%=:\nmbarrier.try_wait.parity.shared::cta.b64 p, [%0], %1;\n@p bra D_%=;\n"
               "add.u32 n, n, 1;\nsetp.lt.u32 p, n, %2;\n@p bra W_%=;\ntrap;\nD_%=:\n}\n" ::"r"(bar), "r"(parity), "n"(SPIN_LIMIT) : "memory");
}
__device__ __forceinline__ void fence_async() { asm volatile("fence.proxy.async.shared::cta;" ::: "memory"); }
__device__ __forceinline__ void bar_sync(int id) { asm volatile("bar.sync %0, 128;" ::"r"(id) : "memory"); }
__device__ __forceinline__ void tma2d(uint32_t dst, const CUtensorMap* m, int c0, int c1, uint32_t bar) {
  asm volatile("cp.async.bulk.tensor.2d.shared::cluster.global.mbarrier::complete_tx::bytes [%0], [%1, {%3, %4}], [%2];"
               ::"r"(dst), "l"(m), "r"(bar), "r"(c0), "r"(c1) : "memory");
}
__device__ __forceinline__ void tma2d_mc(uint32_t dst, const CUtensorMap* m, int c0, int c1, uint32_t bar) {
  asm volatile("cp.async.bulk.tensor.2d.shared::cluster.global.mbarrier::complete_tx::bytes.multicast::cluster [%0], [%1, {%3, %4}], [%2], %5;"
               ::"r"(dst), "l"(m), "r"(bar), "r"(c0), "r"(c1), "h"((uint16_t)3) : "memory");
}
__device__ __forceinline__ void tma3d(uint32_t dst, const CUtensorMap* m, int c0, int c1, int c2, uint32_t bar) {
  asm volatile("cp.async.bulk.tensor.3d.shared::cluster.global.mbarrier::complete_tx::bytes [%0], [%1, {%3, %4, %5}], [%2];"
               ::"r"(dst), "l"(m), "r"(bar), "r"(c0), "r"(c1), "r"(c2) : "memory");
}
__device__ __forceinline__ void bulk_ld(uint32_t dst, const void* src, int bytes, uint32_t bar) {
  asm volatile("cp.async.bulk.shared::cluster.global.mbarrier::complete_tx::bytes [%0], [%1], %2, [%3];" ::"r"(dst), "l"(src), "r"(bytes), "r"(bar) : "memory");
}
__device__ __forceinline__ void bulk_ld_mc(uint32_t dst, const void* src, int bytes, uint32_t bar) {
  asm volatile("cp.async.bulk.shared::cluster.global.mbarrier::complete_tx::bytes.multicast::cluster [%0], [%1], %2, [%3], %4;"
               ::"r"(dst), "l"(src), "r"(bytes), "r"(bar), "h"((uint16_t)3) : "memory");
}
__device__ __forceinline__ void tma2d_st(const CUtensorMap* m, uint32_t src, int c0, int c1) {
  asm volatile("cp.async.bulk.tensor.2d.global.shared::cta.bulk_group [%0, {%2, %3}], [%1];" ::"l"(m), "r"(src), "r"(c0), "r"(c1) : "memory");
}
__device__ __forceinline__ void pf_l2(const void* p, int bytes) { asm volatile("cp.async.bulk.prefetch.L2.global [%0], %1;" ::"l"(p), "r"(bytes) : "memory"); }
__device__ __forceinline__ void pf_t2d(const CUtensorMap* m, int c0, int c1) {
  asm volatile("cp.async.bulk.prefetch.tensor.2d.L2.global [%0, {%1, %2}];" ::"l"(m), "r"(c0), "r"(c1) : "memory");
}
__device__ __forceinline__ void pf_t3d(const CUtensorMap* m, int c0, int c1, int c2) {
  asm volatile("cp.async.bulk.prefetch.tensor.3d.L2.global [%0, {%1, %2, %3}];" ::"l"(m), "r"(c0), "r"(c1), "r"(c2) : "memory");
}
__device__ __forceinline__ void ldsm4(uint32_t (&r)[4], uint32_t a) {
  asm volatile("ldmatrix.sync.aligned.m8n8.x4.shared.b16 {%0,%1,%2,%3}, [%4];" : "=r"(r[0]), "=r"(r[1]), "=r"(r[2]), "=r"(r[3]) : "r"(a) : "memory");
}
__device__ __forceinline__ void ldsm4t(uint32_t (&r)[4], uint32_t a) {
  asm volatile("ldmatrix.sync.aligned.m8n8.x4.trans.shared.b16 {%0,%1,%2,%3}, [%4];" : "=r"(r[0]), "=r"(r[1]), "=r"(r[2]), "=r"(r[3]) : "r"(a) : "memory");
}
__device__ __forceinline__ void stsm4(uint32_t a, uint32_t r0, uint32_t r1, uint32_t r2, uint32_t r3) {
  asm volatile("stmatrix.sync.aligned.m8n8.x4.shared.b16 [%0], {%1,%2,%3,%4};" ::"r"(a), "r"(r0), "r"(r1), "r"(r2), "r"(r3) : "memory");
}
__device__ __forceinline__ uint32_t pk2(float lo, float hi) { uint32_t r; asm("cvt.rn.bf16x2.f32 %0, %1, %2;" : "=r"(r) : "f"(hi), "f"(lo)); return r; }
__device__ __forceinline__ uint32_t hmul(uint32_t a, uint32_t b) { uint32_t r; asm("mul.rn.bf16x2 %0, %1, %2;" : "=r"(r) : "r"(a), "r"(b)); return r; }
__device__ __forceinline__ uint32_t hadd(uint32_t a, uint32_t b) { uint32_t r; asm("add.rn.bf16x2 %0, %1, %2;" : "=r"(r) : "r"(a), "r"(b)); return r; }
__device__ __forceinline__ uint32_t hmax(uint32_t a, uint32_t b) { uint32_t r; asm("max.bf16x2 %0, %1, %2;" : "=r"(r) : "r"(a), "r"(b)); return r; }
__device__ __forceinline__ uint32_t hmin(uint32_t a, uint32_t b) { uint32_t r; asm("min.bf16x2 %0, %1, %2;" : "=r"(r) : "r"(a), "r"(b)); return r; }
__device__ __forceinline__ float ex2(float x) { float r; asm("ex2.approx.ftz.f32 %0, %1;" : "=f"(r) : "f"(x)); return r; }
__device__ __forceinline__ float rcp_fast(float x) { float r; asm("rcp.approx.ftz.f32 %0, %1;" : "=f"(r) : "f"(x)); return r; }
__device__ __forceinline__ uint32_t phi2(float lo, float hi) {
  uint32_t t = pk2(lo, hi);
  uint32_t e = pk2(ex2(lo * 1.4426950408889634f), ex2(hi * 1.4426950408889634f));
  return hadd(hmax(t, 0x35863586u), hmin(e, 0x3F803F80u));
}
__device__ __forceinline__ void poll_ge(const unsigned* p, unsigned target) {
#pragma unroll 1
  for (int n = 0; n < SPIN_LIMIT; n++) {
    unsigned v;
    asm volatile("ld.acquire.gpu.global.u32 %0, [%1];" : "=r"(v) : "l"(p) : "memory");
    if ((int)(v - target) >= 0) return;
  }
  __trap();
}

struct Params {
  CUtensorMap tmX, tmW, tmWo, tmK, tmV, tmQ, tmH, tmOA, tmOB;
  const __nv_bfloat16 *q, *k, *v, *shift_k, *h, *D, *wo;
  __nv_bfloat16* out;
};

__global__ void __cluster_dims__(2, 1, 1) __launch_bounds__(384, 1) fused_kernel(const __grid_constant__ Params P) {
  extern __shared__ __align__(1024) uint8_t smem[];
  const uint32_t sb = smem_u32(smem);
  const uint32_t bars = sb + OFF_BAR;
  const int tid = threadIdx.x, warp = tid >> 5, lane = tid & 31;
  const int rank = blockIdx.x & 1, cl = blockIdx.x >> 1;
  const int mb = cl >> 3, hq = cl & 7;
  const int hp = 2 * hq + rank;
  const int rb = 2 * mb + (hq >> 2), cb = hq & 3;
  const int ch0 = blockIdx.x * 8;
#define BAR(i) (bars + 8 * (i))

  if (tid == 0) { STAMP(0, 0); GSTAMP(0, 30); }
  if (lane == 0) {
    const int wu = __shfl_sync(1u, warp, 0);
#pragma unroll
    for (int r = 0; r < 5; r++) {
      constexpr uint64_t CNT[5] = {0x882411444111ull, 0x118111111444ull, 0x222222222222ull, 0x444444442222ull, 0x000022222444ull};
      if (r < 4 || wu < 8) mbar_init(BAR(12 * r + wu), (uint32_t)(CNT[r] >> (4 * wu)) & 15);
    }
    asm volatile("fence.mbarrier_init.release.cluster;" ::: "memory");
  }
  asm volatile("barrier.cluster.arrive.relaxed.aligned;\nbarrier.cluster.wait.aligned;" ::: "memory");

  if (warp < 8) {
    asm volatile("setmaxnreg.inc.sync.aligned.u32 224;");
    const int wg = warp >> 2, w = warp & 3, g = lane >> 2, q = lane & 3, t = tid & 127;
    const bool elect = (t == 0);
    uint32_t pq[2][16];
    {
      float acc[2][96];
      int st = 0, ph = 0;
      for (int kb = 0; kb < 16; kb++) {
        mbar_wait(BAR(B_FULL1 + st), ph);
        if (kb == 0 && elect) { STAMP(wg, 1); GSTAMP(wg, 26); }
        if (kb == 8 && elect) { STAMP(wg, 16); GSTAMP(wg, 25); }
        const uint32_t sa = sb + st * STAGE_BYTES;
        const uint64_t da = mkdesc(sa + wg * 16384, 16, 1024, 1), db = mkdesc(sa + 32768, 8192, 1024, 1);
        wg_fence();
#pragma unroll
        for (int ks = 0; ks < 4; ks++) {
          wgmma_ss_n192<0, 1>(acc[0], da + ks * 2, db + ks * 128, (kb | ks) != 0);
          wgmma_ss_n192<0, 1>(acc[1], da + 512 + ks * 2, db + ks * 128, (kb | ks) != 0);
        }
        wg_commit();
        wg_wait<1>();
        if (kb > 0 && t < 2) mbar_arrive_cl(BAR(B_EMPTY1 + (st == 0 ? 2 : st - 1)), t);
        if (++st == 3) { st = 0; ph ^= 1; }
      }
      wg_wait<0>();
      keep(acc[0]); keep(acc[1]);
      if (t < 2) mbar_arrive_cl(BAR(B_EMPTY1 + 0), t);
      if (elect) { STAMP(wg, 2); GSTAMP(wg, 27); }
      const uint32_t lrow = (16 * w + 8 * ((lane >> 3) & 1) + (lane & 7)) * 128 + (((lane >> 4) ^ (lane & 7)) << 4);
      const uint32_t pkb = sb + OFF_PK + wg * 16384, vb = sb + OFF_V + wg * 16384;
#pragma unroll
      for (int mt = 0; mt < 2; mt++)
#pragma unroll
        for (int cp = 0; cp < 4; cp++) {
          const float* a = &acc[mt][32 + 8 * cp];
          const float* b = &acc[mt][64 + 8 * cp];
          const uint32_t o = (lrow ^ (cp * 32)) + mt * 8192;
          stsm4(pkb + o, phi2(a[0], a[1]), phi2(a[2], a[3]), phi2(a[4], a[5]), phi2(a[6], a[7]));
          stsm4(vb + o, pk2(b[0], b[1]), pk2(b[2], b[3]), pk2(b[4], b[5]), pk2(b[6], b[7]));
        }
      fence_async();
      mbar_wait(BAR(B_XT), 0);
      bar_sync(1 + wg);
      if (elect) STAMP(wg, 3);
      float kva[36];
      wg_fence();
#pragma unroll
      for (int ks = 0; ks < 8; ks++)
        wgmma_ss_n72<1, 1>(kva, mkdesc(pkb + ks * 2048, 16, 1024, 1), mkdesc(vb + ks * 2048, sb + OFF_ONES - (vb + ks * 2048), 1024, 1), ks != 0);
      wg_commit();
#pragma unroll
      for (int i = 0; i < 16; i++) pq[0][i] = phi2(acc[0][2 * i], acc[0][2 * i + 1]);
      wg_wait<0>();
      keep(kva);
      {
        const unsigned par = *(volatile unsigned*)(smem + OFF_BAR + 512) & 1;
        float* dst = &g_kv[par][hp][0];
#pragma unroll
        for (int c = 0; c < 4; c++) {
          float v0 = w < 2 ? kva[4 * c] : kva[16 + 4 * c], v1 = w < 2 ? kva[4 * c + 1] : kva[17 + 4 * c];
          float v2 = w < 2 ? kva[4 * c + 2] : kva[18 + 4 * c], v3 = w < 2 ? kva[4 * c + 3] : kva[19 + 4 * c];
          asm volatile("red.global.add.v4.f32 [%0], {%1,%2,%3,%4};" ::"l"(dst + (c * 128 + t) * 4), "f"(v0), "f"(v1), "f"(v2), "f"(v3) : "memory");
        }
        if (q < 2) asm volatile("red.global.add.f32 [%0], %1;" ::"l"(dst + 2048 + 16 * w + g + 8 * q), "f"(q ? kva[34] : kva[32]) : "memory");
        __syncwarp();
        if (lane == 0) mbar_arrive(BAR(B_PKFREE));
      }
      if (elect) STAMP(wg, 4);
#pragma unroll
      for (int i = 0; i < 16; i++) pq[1][i] = phi2(acc[1][2 * i], acc[1][2 * i + 1]);
    }
    uint32_t a1[2][4], a4[4][4];
    float twr[4], twi[4];
    {
      const uint4* ct = (const uint4*)c_thr + t;
#pragma unroll
      for (int s = 0; s < 2; s++) { uint4 u = __ldg(ct + s * 128); a1[s][0] = u.x; a1[s][1] = u.y; a1[s][2] = u.z; a1[s][3] = u.w; }
#pragma unroll
      for (int s = 0; s < 4; s++) { uint4 u = __ldg(ct + (2 + s) * 128); a4[s][0] = u.x; a4[s][1] = u.y; a4[s][2] = u.z; a4[s][3] = u.w; }
      uint4 u = __ldg(ct + 6 * 128), v = __ldg(ct + 7 * 128);
      twr[0] = __uint_as_float(u.x); twr[1] = __uint_as_float(u.y); twr[2] = __uint_as_float(u.z); twr[3] = __uint_as_float(u.w);
      twi[0] = __uint_as_float(v.x); twi[1] = __uint_as_float(v.y); twi[2] = __uint_as_float(v.z); twi[3] = __uint_as_float(v.w);
    }
    uint2 dd = __ldg((const uint2*)(P.D + ch0 + 4 * wg));
    if (q != 0) dd = make_uint2(0, 0);
    mbar_wait(BAR(B_EMPTY1 + 2), 0);
    if (elect) STAMP(wg, 5);
    const uint32_t vp = sb + OFF_VP + wg * 8192;
    const uint32_t vpl = vp + (16 * w + 8 * (lane >> 4) + (lane & 7)) * 128 + ((((lane >> 3) & 1) ^ (lane & 7)) << 4);
#pragma unroll 1
    for (int i = 0; i < 4; i++) {
      if (i == 2) {
        if (elect) STAMP(wg, 8);
        mbar_wait(BAR(B_KV), 0);
        if (elect) STAMP(wg, 9);
        float oa[4][20];
        wg_fence();
#pragma unroll
        for (int mt = 0; mt < 2; mt++)
#pragma unroll
          for (int hh = 0; hh < 2; hh++)
#pragma unroll
            for (int ks = 0; ks < 2; ks++) {
              const uint32_t* a = &pq[mt][8 * hh + 4 * ks];
              wgmma_rs_n40<1>(oa[2 * mt + hh], a[0], a[1], a[2], a[3], mkdesc(sb + OFF_KVB + hh * 2560 + ks * 256, 128, 512, 0), ks);
            }
        wg_commit();
        wg_wait<0>();
        uint4* ot = g_o + ((2 * mb + wg) * 16 + hp) * 1024 + (16 * w + g) * 8;
#pragma unroll
        for (int mt = 0; mt < 2; mt++)
#pragma unroll
          for (int hh = 0; hh < 2; hh++) {
            float (&o)[20] = oa[2 * mt + hh];
            keep(o);
            const uint32_t den = hadd(pk2(o[16], o[18]), 0x35863586u);
#pragma unroll
            for (int r = 0; r < 2; r++) {
              const float ri = rcp_fast(__uint_as_float(r ? (den & 0xFFFF0000u) : (den << 16)));
              uint4 u;
              u.x = pk2(o[2 * r] * ri, o[2 * r + 1] * ri);
              u.y = pk2(o[4 + 2 * r] * ri, o[5 + 2 * r] * ri);
              u.z = pk2(o[8 + 2 * r] * ri, o[9 + 2 * r] * ri);
              u.w = pk2(o[12 + 2 * r] * ri, o[13 + 2 * r] * ri);
              __stcg(ot + (64 * mt + 8 * r) * 8 + ((4 * hh + q) ^ g), u);
            }
          }
        __syncwarp();
        if (lane == 0) mbar_arrive(BAR(B_ODONE));
        if (elect) STAMP(wg, 10);
      }
      const uint32_t xt = sb + OFF_XT + (4 * wg + i) * XT_STRIDE;
      const uint32_t hb = sb + OFF_H + (i >> 1) * 16384 + (2 * wg + (i & 1)) * 4096;
      if (!(i & 1)) mbar_wait(BAR(B_H + (i >> 1)), 0);
      float ux[32], uh[32];
      wg_fence();
#pragma unroll
      for (int s = 0; s < 2; s++) wgmma_rs_n64<1>(ux, a1[s][0], a1[s][1], a1[s][2], a1[s][3], mkdesc(xt + s * 256, 128, 512, 0), s);
      wg_commit();
#pragma unroll
      for (int s = 0; s < 2; s++) wgmma_rs_n64<1>(uh, a1[s][0], a1[s][1], a1[s][2], a1[s][3], mkdesc(hb + s * 512, 1024, 256, 3), s);
      wg_commit();
      float X[2][16], H[2][16];
      const uint64_t df = mkdesc(sb + OFF_F2F, 128, 512, 0), di = mkdesc(sb + OFF_F2I, 128, 512, 0);
      auto stage2 = [&](float (&u)[32], float (&Z)[2][16]) {
        uint32_t fr[8], fi[8];
#pragma unroll
        for (int c = 0; c < 8; c++) {
          const int h2 = 2 * (c & 1);
          const float r0 = u[4 * c], r1 = u[4 * c + 1], i0 = u[4 * c + 2], i1 = u[4 * c + 3];
          fr[c] = pk2(r0 * twr[h2] - i0 * twi[h2], r1 * twr[h2 + 1] - i1 * twi[h2 + 1]);
          fi[c] = pk2(r0 * twi[h2] + i0 * twr[h2], r1 * twi[h2 + 1] + i1 * twr[h2 + 1]);
        }
        wg_fence();
#pragma unroll
        for (int p = 0; p < 2; p++) {
          wgmma_rs_n32<0>(Z[p], fr[4 * p], fr[4 * p + 2], fr[4 * p + 1], fr[4 * p + 3], df, 0);
          wgmma_rs_n32<0>(Z[p], fi[4 * p], fi[4 * p + 2], fi[4 * p + 1], fi[4 * p + 3], df + 16, 1);
        }
        wg_commit();
      };
      wg_wait<1>();
      keep(ux);
      stage2(ux, X);
      wg_wait<1>();
      keep(uh);
      {
        const uint32_t dw = (i & 2) ? dd.y : dd.x;
        uh[0] += __uint_as_float((i & 1) ? (dw & 0xFFFF0000u) : (dw << 16));
      }
      stage2(uh, H);
      wg_wait<0>();
      keep(X[0]); keep(X[1]); keep(H[0]); keep(H[1]);
      float V[2][16];
      {
        uint32_t pr[4][2], pi[4][2];
#pragma unroll
        for (int j = 0; j < 4; j++)
#pragma unroll
          for (int c = 0; c < 2; c++) {
            float sr[2], si[2];
#pragma unroll
            for (int e = 0; e < 2; e++) {
              sr[e] = 0.f; si[e] = 0.f;
#pragma unroll
              for (int a = 0; a <= j; a++) {
                const int b = j - a;
                const float hr = H[a >> 1][4 * c + 2 * (a & 1) + e], hi = H[a >> 1][8 + 4 * c + 2 * (a & 1) + e];
                const float xr = X[b >> 1][4 * c + 2 * (b & 1) + e], xi = X[b >> 1][8 + 4 * c + 2 * (b & 1) + e];
                sr[e] = a == 0 ? hr * xr : fmaf(hr, xr, sr[e]);
                si[e] = a == 0 ? hr * xi : fmaf(hr, xi, si[e]);
                sr[e] = fmaf(-hi, xi, sr[e]);
                si[e] = fmaf(hi, xr, si[e]);
              }
            }
            pr[j][c] = pk2(sr[0], sr[1]);
            pi[j][c] = pk2(si[0], si[1]);
          }
        wg_fence();
#pragma unroll
        for (int p = 0; p < 2; p++) {
          wgmma_rs_n32<0>(V[p], pr[2 * p][0], pr[2 * p + 1][0], pr[2 * p][1], pr[2 * p + 1][1], di, 0);
          wgmma_rs_n32<0>(V[p], pi[2 * p][0], pi[2 * p + 1][0], pi[2 * p][1], pi[2 * p + 1][1], di + 16, 1);
        }
        wg_commit();
      }
      wg_wait<0>();
      keep(V[0]); keep(V[1]);
#pragma unroll
      for (int j = 0; j < 4; j++) {
        uint32_t wr[2], wi[2];
#pragma unroll
        for (int c = 0; c < 2; c++) {
          const float* vr = &V[j >> 1][4 * c + 2 * (j & 1)];
          const float* vi = vr + 8;
          wr[c] = pk2(vr[0] * twr[2 * c] + vi[0] * twi[2 * c], vr[1] * twr[2 * c + 1] + vi[1] * twi[2 * c + 1]);
          wi[c] = pk2(vi[0] * twr[2 * c] - vr[0] * twi[2 * c], vi[1] * twr[2 * c + 1] - vr[1] * twi[2 * c + 1]);
        }
        stsm4(vpl ^ (j * 32), wr[0], wr[1], wi[0], wi[1]);
      }
      fence_async();
      bar_sync(1 + wg);
      if ((i & 1) && t < 2) mbar_arrive_cl(BAR(B_HFREE + (i >> 1)), t);
      float y[32];
      wg_fence();
#pragma unroll
      for (int s = 0; s < 4; s++) wgmma_rs_n64<1>(y, a4[s][0], a4[s][1], a4[s][2], a4[s][3], mkdesc(vp + s * 2048, 16, 1024, 1), s);
      wg_commit();
      wg_wait<0>();
      keep(y);
      uint32_t yo[8];
#pragma unroll
      for (int c = 0; c < 8; c++)
        yo[c] = c < 2 ? pk2(y[4 * c], y[4 * c + 1]) : pk2(y[4 * c] + y[4 * c - 6], y[4 * c + 1] + y[4 * c - 5]);
      const uint32_t ya = xt + (lane >> 3) * 512 + (8 * w + (lane & 7)) * 16;
      stsm4(ya, yo[0], yo[1], yo[2], yo[3]);
      stsm4(ya + 2048, yo[4], yo[5], yo[6], yo[7]);
      bar_sync(1 + wg);
      if (elect) STAMP(wg, i < 2 ? 6 + i : 9 + i);
    }
    if (t < 2) mbar_arrive_cl(BAR(B_VFREE), t);
    __syncwarp();
    if (lane == 0) mbar_arrive(BAR(B_Y));
    {
      float acc[64];
      for (int kb = 0; kb < 16; kb++) {
        mbar_wait(BAR(B_FULL2 + kb), 0);
        if (kb == 0 && elect) { STAMP(wg, 13); GSTAMP(wg, 28); }
        const uint32_t sa = sb + ((uint32_t)(SLOT_A >> (4 * kb)) & 15) * 16384 + wg * 8192;
        const uint32_t sbb = sb + ((uint32_t)(SLOT_B >> (4 * kb)) & 15) * 16384;
        const uint64_t da = mkdesc(sa, 16, 1024, 1), db = mkdesc(sbb, 8192, 1024, 1);
        wg_fence();
#pragma unroll
        for (int ks = 0; ks < 4; ks++) wgmma_ss_n128<0, 1>(acc, da + ks * 2, db + ks * 128, (kb | ks) != 0);
        wg_commit();
        wg_wait<1>();
        if (kb > 0 && t < 2 && (kb <= 11 || t == rank)) mbar_arrive_cl(BAR(B_CONS2 + kb - 1), t);
      }
      wg_wait<0>();
      keep(acc);
      if (elect) { STAMP(wg, 14); GSTAMP(wg, 29); }
      mbar_wait(BAR(B_CONS2 + 12), 0);
      const uint32_t stg = sb + (wg ? 9 : 3) * 16384;
      const uint32_t lrow = stg + (16 * w + 8 * ((lane >> 3) & 1) + (lane & 7)) * 128 + (((lane >> 4) ^ (lane & 7)) << 4);
#pragma unroll
      for (int cp = 0; cp < 8; cp++) {
        const float* a = &acc[8 * cp];
        stsm4((lrow ^ ((cp & 3) * 32)) + (cp >> 2) * 8192, pk2(a[0], a[1]), pk2(a[2], a[3]), pk2(a[4], a[5]), pk2(a[6], a[7]));
      }
      fence_async();
      bar_sync(1 + wg);
      if (elect) {
        const int col = 1024 + 256 * cb + 128 * rank, row = 128 * rb + 64 * wg;
        tma2d_st(&P.tmOB, stg, col, row);
        tma2d_st(&P.tmOB, stg + 8192, col + 64, row);
        asm volatile("cp.async.bulk.commit_group;\ncp.async.bulk.wait_group.read 0;" ::: "memory");
        STAMP(wg, 15); GSTAMP(wg, 31);
      }
    }
  } else {
    asm volatile("setmaxnreg.dec.sync.aligned.u32 56;");
    if (warp == 8) {
      if (lane == 0) {
        int st = 0, ph = 1;
        for (int kb = 0; kb < 16; kb++) {
          if (kb >= 3) mbar_wait(BAR(B_EMPTY1 + st), ph);
          const uint32_t sa = sb + st * STAGE_BYTES;
          mbar_expect(BAR(B_FULL1 + st), STAGE_BYTES);
          tma2d_mc(sa + rank * 16384, &P.tmX, kb * 64, mb * 256 + rank * 128, BAR(B_FULL1 + st));
          tma3d(sa + 32768, &P.tmW, hp * 64, kb * 64, 0, BAR(B_FULL1 + st));
          if (kb == 2) { mbar_expect(BAR(B_XT), 6144); bulk_ld(sb + OFF_ONES, c_img, 6144, BAR(B_XT)); }
          if (++st == 3) { st = 0; ph ^= 1; }
        }
        STAMP(2, 1);
        const unsigned epoch = g_epoch[blockIdx.x];
        auto loadB = [&](int kb) {
          mbar_expect(BAR(B_FULL2 + kb), 16384);
          tma3d(sb + ((uint32_t)(SLOT_B >> (4 * kb)) & 15) * 16384, &P.tmWo, 0, kb * 64, 4 * cb + 2 * rank, BAR(B_FULL2 + kb));
        };
        auto loadA = [&](int kb) {
          mbar_expect(BAR(B_FULL2 + kb), 16384);
          bulk_ld_mc(sb + ((uint32_t)(SLOT_A >> (4 * kb)) & 15) * 16384 + rank * 8192, g_o + (rb * 16 + kb) * 1024 + rank * 512, 8192, BAR(B_FULL2 + kb));
        };
        mbar_wait(BAR(B_EMPTY1 + 1), 0);
        for (int i = 0; i < 4; i++) {
          if (!(i & 1)) mbar_expect(BAR(B_H + (i >> 1)), 16384);
          tma2d(sb + OFF_H + i * 8192, &P.tmH, 0, (ch0 + 4 * (i & 1) + (i & 2)) * 128, BAR(B_H + (i >> 1)));
        }
        loadB(0);
        mbar_wait(BAR(B_EMPTY1 + 0), 1);
        loadB(1); loadB(2);
        mbar_wait(BAR(B_PKFREE), 0);
        for (int kb = 3; kb < 7; kb++) loadB(kb);
        STAMP(2, 2);
        poll_ge(&g_ocnt[rb * 32], 16 * (epoch + 1));
        asm volatile("fence.proxy.async.global;" ::: "memory");
        STAMP(2, 3);
        for (int kb = 0; kb < 3; kb++) { mbar_wait(BAR(B_HFREE + kb), 0); loadA(kb); }
        STAMP(2, 4);
        for (int j = 0; j < 11; j++) {
          mbar_wait(BAR(B_CONS2 + j), 0);
          if (j < 2) { loadA(3 + 2 * j); loadA(4 + 2 * j); } else { loadA(j + 5); loadB(j + 5); }
        }
        g_epoch[blockIdx.x] = epoch + 1;
        STAMP(2, 5);
      }
    } else {
      const int hw = warp - 9, g = lane >> 2;
      const unsigned epoch = g_epoch[blockIdx.x];
      if (hw == 0) {
        if (lane == 0) *(volatile unsigned*)(smem + OFF_BAR + 512) = epoch;
        float* z = &g_kv[(epoch & 1) ^ 1][hp][mb * 272];
        for (int i = lane; i < 272; i += 32) z[i] = 0.f;
      }
      uint32_t tap[4];
      {
        const uint2 u = __ldg((const uint2*)(P.shift_k + (ch0 + g) * 4));
        tap[0] = __byte_perm(u.x, 0, 0x1010); tap[1] = __byte_perm(u.x, 0, 0x3232);
        tap[2] = __byte_perm(u.y, 0, 0x1010); tap[3] = __byte_perm(u.y, 0, 0x3232);
      }
      mbar_wait(BAR(B_FULL1 + 0), 0);
      if (lane == 0) STAMP(3, hw);
      const uint32_t stg = sb + OFF_STG + hw * STG_STRIDE;
      const uint32_t xtl = sb + OFF_XT + (lane & 7) * XT_STRIDE + ((lane >> 3) & 1) * 512 + (lane >> 4) * 16;
      int ph = 0;
      for (int ci = hw; ci < 16; ci += 3) {
        if (lane == 0) {
          mbar_expect(BAR(B_STG + 2 * hw), 2176 + 2048);
          tma2d(stg, &P.tmK, ch0, 128 * ci - 8, BAR(B_STG + 2 * hw));
          tma2d(stg + 2176, &P.tmV, ch0, 128 * ci, BAR(B_STG + 2 * hw));
        }
        mbar_wait(BAR(B_STG + 2 * hw), ph);
        ph ^= 1;
#pragma unroll 1
        for (int grp = 0; grp < 4; grp++) {
          uint32_t vv[4], o[4];
          ldsm4t(vv, stg + 2176 + (32 * grp + lane) * 16);
#pragma unroll
          for (int rg = 0; rg < 4; rg++) {
            uint32_t kk[4];
            ldsm4t(kk, stg + (8 + 32 * grp + 8 * rg + (lane & 7) - (lane >> 3)) * 16);
            uint32_t s = hadd(hadd(hadd(hmul(kk[3], tap[3]), hmul(kk[2], tap[2])), hmul(kk[1], tap[1])), hmul(kk[0], tap[0]));
            o[rg] = hmul(s, vv[rg]);
          }
          stsm4(xtl + (ci >> 2) * 1024 + ((ci & 3) * 8 + 2 * grp) * 16, o[0], o[1], o[2], o[3]);
        }
        __syncwarp();
      }
      fence_async();
      __syncwarp();
      if (lane == 0) {
        mbar_arrive(BAR(B_XT));
        STAMP(3, 3 + hw);
      }
      if (hw == 2) {
        if (lane == 0) {
          mbar_wait(BAR(B_PKFREE), 0);
          __threadfence();
          atomicAdd(&g_kvcnt[hp * 32], 1);
          STAMP(3, 6);
          mbar_wait(BAR(B_ODONE), 0);
          __threadfence();
          atomicAdd(&g_ocnt[(2 * mb) * 32], 1);
          atomicAdd(&g_ocnt[(2 * mb + 1) * 32], 1);
          STAMP(3, 7);
        }
        __syncwarp();
      } else {
        if (lane == 0) { mbar_wait(BAR(B_PKFREE), 0); poll_ge(&g_kvcnt[hp * 32], 8 * (epoch + 1)); }
        __syncwarp();
        if (lane == 0 && hw == 0) STAMP(3, 8);
        const float* src = &g_kv[epoch & 1][hp][0];
        const int t = hw * 32 + lane;
        const float zf = __ldcg(src + 2048 + t);
#pragma unroll
        for (int hh = 0; hh < 2; hh++) {
          float4 f[4];
#pragma unroll
          for (int c = 0; c < 4; c++) f[c] = __ldcg((const float4*)src + c * 128 + hh * 64 + t);
          uint8_t* dst = smem + OFF_KVB + hh * 2560 + (lane & 3) * 512 + (16 * hw + g) * 16;
          *(uint4*)dst = make_uint4(pk2(f[0].x, f[0].y), pk2(f[1].x, f[1].y), pk2(f[2].x, f[2].y), pk2(f[3].x, f[3].y));
          *(uint4*)(dst + 128) = make_uint4(pk2(f[0].z, f[0].w), pk2(f[1].z, f[1].w), pk2(f[2].z, f[2].w), pk2(f[3].z, f[3].w));
        }
        const uint32_t zz = pk2(zf, zf);
        *(uint4*)(smem + OFF_KVB + hw * 2560 + 2048 + lane * 16) = make_uint4(zz, zz, zz, zz);
        fence_async();
        __syncwarp();
        if (lane == 0) { mbar_arrive(BAR(B_KV)); if (hw == 0) STAMP(3, 9); }
      }
      {
        const uint32_t* qp = (const uint32_t*)(P.q + ch0) + g * 512 + (lane & 3);
        uint32_t* op = (uint32_t*)(P.out + ch0) + g * 1024 + (lane & 3);
#pragma unroll 1
        for (int bt = hw; bt < 8; bt += 3) {
          uint32_t qq[32];
#pragma unroll
          for (int i = 0; i < 32; i++)
            asm volatile("ld.global.nc.L1::no_allocate.b32 %0, [%1];" : "=r"(qq[i]) : "l"(qp + (bt * 32 + i) * 4096));
          mbar_wait(BAR(B_Y), 0);
#pragma unroll
          for (int grp = 0; grp < 8; grp++) {
            uint32_t yy[4];
            ldsm4t(yy, xtl + (bt >> 1) * 1024 + ((bt & 1) * 16 + 2 * grp) * 16);
#pragma unroll
            for (int m = 0; m < 4; m++) op[(bt * 32 + grp * 4 + m) * 8192] = hmul(yy[m], qq[grp * 4 + m]);
          }
        }
      }
      if (lane == 0) STAMP(3, 10 + hw);
    }
  }
}

typedef CUresult (*EncodeFn)(CUtensorMap*, CUtensorMapDataType, cuuint32_t, void*, const cuuint64_t*, const cuuint64_t*,
                             const cuuint32_t*, const cuuint32_t*, CUtensorMapInterleave, CUtensorMapSwizzle,
                             CUtensorMapL2promotion, CUtensorMapFloatOOBfill);

static void enc(EncodeFn fn, CUtensorMap* m, const void* p, int rank, const cuuint64_t* dims, const cuuint64_t* strides,
                const cuuint32_t* box, CUtensorMapSwizzle swz, CUtensorMapL2promotion promo) {
  cuuint32_t es[3] = {1, 1, 1};
  fn(m, CU_TENSOR_MAP_DATA_TYPE_BFLOAT16, rank, (void*)p, dims, strides, box, es, CU_TENSOR_MAP_INTERLEAVE_NONE, swz, promo,
     CU_TENSOR_MAP_FLOAT_OOB_FILL_NONE);
}

extern "C" void kernel_launch(void* const* d_in, const int* in_sizes, int n_in, void* d_out, int out_size) {
  void* fp = nullptr;
  cudaDriverEntryPointQueryResult qr;
  cudaGetDriverEntryPoint("cuTensorMapEncodeTiled", &fp, cudaEnableDefault, &qr);
  EncodeFn fn = (EncodeFn)fp;
  Params P;
  P.q = (const __nv_bfloat16*)d_in[0]; P.k = (const __nv_bfloat16*)d_in[1]; P.v = (const __nv_bfloat16*)d_in[2];
  P.shift_k = (const __nv_bfloat16*)d_in[3]; P.h = (const __nv_bfloat16*)d_in[4]; P.D = (const __nv_bfloat16*)d_in[5];
  P.wo = (const __nv_bfloat16*)d_in[8];
  P.out = (__nv_bfloat16*)d_out;
  const CUtensorMapSwizzle S128 = CU_TENSOR_MAP_SWIZZLE_128B, S32 = CU_TENSOR_MAP_SWIZZLE_32B, S0 = CU_TENSOR_MAP_SWIZZLE_NONE;
  const CUtensorMapL2promotion P0 = CU_TENSOR_MAP_L2_PROMOTION_NONE, P128 = CU_TENSOR_MAP_L2_PROMOTION_L2_128B;
  { cuuint64_t d[2] = {1024, 2048}, s[1] = {2048}; cuuint32_t b[2] = {64, 128}; enc(fn, &P.tmX, d_in[6], 2, d, s, b, S128, P128); }
  { cuuint64_t d[3] = {1024, 1024, 3}, s[2] = {6144, 2048}; cuuint32_t b[3] = {64, 64, 3}; enc(fn, &P.tmW, d_in[7], 3, d, s, b, S128, P128); }
  { cuuint64_t d[3] = {64, 1024, 16}, s[2] = {2048, 128}; cuuint32_t b[3] = {64, 64, 2}; enc(fn, &P.tmWo, d_in[8], 3, d, s, b, S128, P128); }
  { cuuint64_t d[2] = {1024, 2048}, s[1] = {2048}; cuuint32_t b[2] = {8, 136}; enc(fn, &P.tmK, d_in[1], 2, d, s, b, S0, P0); }
  { cuuint64_t d[2] = {1024, 2048}, s[1] = {2048}; cuuint32_t b[2] = {8, 128};
    enc(fn, &P.tmV, d_in[2], 2, d, s, b, S0, P0); enc(fn, &P.tmQ, d_in[0], 2, d, s, b, S0, P0); }
  { cuuint64_t d[2] = {16, 131072}, s[1] = {32}; cuuint32_t b[2] = {16, 256}; enc(fn, &P.tmH, d_in[4], 2, d, s, b, S32, P128); }
  { cuuint64_t d[2] = {2048, 2048}, s[1] = {4096}; cuuint32_t b[2] = {8, 128}; enc(fn, &P.tmOA, d_out, 2, d, s, b, S0, P0); }
  { cuuint64_t d[2] = {2048, 2048}, s[1] = {4096}; cuuint32_t b[2] = {64, 64}; enc(fn, &P.tmOB, d_out, 2, d, s, b, S128, P0); }
  cudaFuncSetAttribute(fused_kernel, cudaFuncAttributeMaxDynamicSharedMemorySize, SMEM_TOTAL);
  fused_kernel<<<128, 384, SMEM_TOTAL>>>(P);
}
```

```cpp
#include <cuda_runtime.h>
#include <cuda_bf16.h>
#include <cuda_fp16.h>
#include <cuda.h>
#include <stdint.h>

template<int TA, int TB, int SA=1> __device__ __forceinline__ void wgmma_ss_n192(float (&d)[96], uint64_t da, uint64_t db, int scale_d) {
  asm volatile("{\n.reg .pred p;\nsetp.ne.b32 p, %98, 0;\n"
    "wgmma.mma_async.sync.aligned.m64n192k16.f32.bf16.bf16 {%0, %1, %2, %3, %4, %5, %6, %7, %8, %9, %10, %11, %12, %13, %14, %15, %16, %17, %18, %19, %20, %21, %22, %23, %24, %25, %26, %27, %28, %29, %30, %31, %32, %33, %34, %35, %36, %37, %38, %39, %40, %41, %42, %43, %44, %45, %46, %47, %48, %49, %50, %51, %52, %53, %54, %55, %56, %57, %58, %59, %60, %61, %62, %63, %64, %65, %66, %67, %68, %69, %70, %71, %72, %73, %74, %75, %76, %77, %78, %79, %80, %81, %82, %83, %84, %85, %86, %87, %88, %89, %90, %91, %92, %93, %94, %95}, %96, %97, p, %101, 1, %99, %100;\n}\n"
    : "+f"(d[0]), "+f"(d[1]), "+f"(d[2]), "+f"(d[3]), "+f"(d[4]), "+f"(d[5]), "+f"(d[6]), "+f"(d[7]), "+f"(d[8]), "+f"(d[9]), "+f"(d[10]), "+f"(d[11]), "+f"(d[12]), "+f"(d[13]), "+f"(d[14]), "+f"(d[15]), "+f"(d[16]), "+f"(d[17]), "+f"(d[18]), "+f"(d[19]), "+f"(d[20]), "+f"(d[21]), "+f"(d[22]), "+f"(d[23]), "+f"(d[24]), "+f"(d[25]), "+f"(d[26]), "+f"(d[27]), "+f"(d[28]), "+f"(d[29]), "+f"(d[30]), "+f"(d[31]), "+f"(d[32]), "+f"(d[33]), "+f"(d[34]), "+f"(d[35]), "+f"(d[36]), "+f"(d[37]), "+f"(d[38]), "+f"(d[39]), "+f"(d[40]), "+f"(d[41]), "+f"(d[42]), "+f"(d[43]), "+f"(d[44]), "+f"(d[45]), "+f"(d[46]), "+f"(d[47]), "+f"(d[48]), "+f"(d[49]), "+f"(d[50]), "+f"(d[51]), "+f"(d[52]), "+f"(d[53]), "+f"(d[54]), "+f"(d[55]), "+f"(d[56]), "+f"(d[57]), "+f"(d[58]), "+f"(d[59]), "+f"(d[60]), "+f"(d[61]), "+f"(d[62]), "+f"(d[63]), "+f"(d[64]), "+f"(d[65]), "+f"(d[66]), "+f"(d[67]), "+f"(d[68]), "+f"(d[69]), "+f"(d[70]), "+f"(d[71]), "+f"(d[72]), "+f"(d[73]), "+f"(d[74]), "+f"(d[75]), "+f"(d[76]), "+f"(d[77]), "+f"(d[78]), "+f"(d[79]), "+f"(d[80]), "+f"(d[81]), "+f"(d[82]), "+f"(d[83]), "+f"(d[84]), "+f"(d[85]), "+f"(d[86]), "+f"(d[87]), "+f"(d[88]), "+f"(d[89]), "+f"(d[90]), "+f"(d[91]), "+f"(d[92]), "+f"(d[93]), "+f"(d[94]), "+f"(d[95])
    : "l"(da), "l"(db), "r"(scale_d), "n"(TA), "n"(TB), "n"(SA));
}
template<int TA, int TB, int SA=1> __device__ __forceinline__ void wgmma_ss_n128(float (&d)[64], uint64_t da, uint64_t db, int scale_d) {
  asm volatile("{\n.reg .pred p;\nsetp.ne.b32 p, %66, 0;\n"
    "wgmma.mma_async.sync.aligned.m64n128k16.f32.bf16.bf16 {%0, %1, %2, %3, %4, %5, %6, %7, %8, %9, %10, %11, %12, %13, %14, %15, %16, %17, %18, %19, %20, %21, %22, %23, %24, %25, %26, %27, %28, %29, %30, %31, %32, %33, %34, %35, %36, %37, %38, %39, %40, %41, %42, %43, %44, %45, %46, %47, %48, %49, %50, %51, %52, %53, %54, %55, %56, %57, %58, %59, %60, %61, %62, %63}, %64, %65, p, %69, 1, %67, %68;\n}\n"
    : "+f"(d[0]), "+f"(d[1]), "+f"(d[2]), "+f"(d[3]), "+f"(d[4]), "+f"(d[5]), "+f"(d[6]), "+f"(d[7]), "+f"(d[8]), "+f"(d[9]), "+f"(d[10]), "+f"(d[11]), "+f"(d[12]), "+f"(d[13]), "+f"(d[14]), "+f"(d[15]), "+f"(d[16]), "+f"(d[17]), "+f"(d[18]), "+f"(d[19]), "+f"(d[20]), "+f"(d[21]), "+f"(d[22]), "+f"(d[23]), "+f"(d[24]), "+f"(d[25]), "+f"(d[26]), "+f"(d[27]), "+f"(d[28]), "+f"(d[29]), "+f"(d[30]), "+f"(d[31]), "+f"(d[32]), "+f"(d[33]), "+f"(d[34]), "+f"(d[35]), "+f"(d[36]), "+f"(d[37]), "+f"(d[38]), "+f"(d[39]), "+f"(d[40]), "+f"(d[41]), "+f"(d[42]), "+f"(d[43]), "+f"(d[44]), "+f"(d[45]), "+f"(d[46]), "+f"(d[47]), "+f"(d[48]), "+f"(d[49]), "+f"(d[50]), "+f"(d[51]), "+f"(d[52]), "+f"(d[53]), "+f"(d[54]), "+f"(d[55]), "+f"(d[56]), "+f"(d[57]), "+f"(d[58]), "+f"(d[59]), "+f"(d[60]), "+f"(d[61]), "+f"(d[62]), "+f"(d[63])
    : "l"(da), "l"(db), "r"(scale_d), "n"(TA), "n"(TB), "n"(SA));
}
template<int TA, int TB, int SA=1> __device__ __forceinline__ void wgmma_ss_n72(float (&d)[36], uint64_t da, uint64_t db, int scale_d) {
  asm volatile("{\n.reg .pred p;\nsetp.ne.b32 p, %38, 0;\n"
    "wgmma.mma_async.sync.aligned.m64n72k16.f32.bf16.bf16 {%0, %1, %2, %3, %4, %5, %6, %7, %8, %9, %10, %11, %12, %13, %14, %15, %16, %17, %18, %19, %20, %21, %22, %23, %24, %25, %26, %27, %28, %29, %30, %31, %32, %33, %34, %35}, %36, %37, p, %41, 1, %39, %40;\n}\n"
    : "+f"(d[0]), "+f"(d[1]), "+f"(d[2]), "+f"(d[3]), "+f"(d[4]), "+f"(d[5]), "+f"(d[6]), "+f"(d[7]), "+f"(d[8]), "+f"(d[9]), "+f"(d[10]), "+f"(d[11]), "+f"(d[12]), "+f"(d[13]), "+f"(d[14]), "+f"(d[15]), "+f"(d[16]), "+f"(d[17]), "+f"(d[18]), "+f"(d[19]), "+f"(d[20]), "+f"(d[21]), "+f"(d[22]), "+f"(d[23]), "+f"(d[24]), "+f"(d[25]), "+f"(d[26]), "+f"(d[27]), "+f"(d[28]), "+f"(d[29]), "+f"(d[30]), "+f"(d[31]), "+f"(d[32]), "+f"(d[33]), "+f"(d[34]), "+f"(d[35])
    : "l"(da), "l"(db), "r"(scale_d), "n"(TA), "n"(TB), "n"(SA));
}
template<int TB, int SA=1> __device__ __forceinline__ void wgmma_rs_n40(float (&d)[20], uint32_t a0, uint32_t a1, uint32_t a2, uint32_t a3, uint64_t db, int scale_d) {
  asm volatile("{\n.reg .pred p;\nsetp.ne.b32 p, %25, 0;\n"
    "wgmma.mma_async.sync.aligned.m64n40k16.f32.bf16.bf16 {%0, %1, %2, %3, %4, %5, %6, %7, %8, %9, %10, %11, %12, %13, %14, %15, %16, %17, %18, %19}, {%20, %21, %22, %23}, %24, p, %27, 1, %26;\n}\n"
    : "+f"(d[0]), "+f"(d[1]), "+f"(d[2]), "+f"(d[3]), "+f"(d[4]), "+f"(d[5]), "+f"(d[6]), "+f"(d[7]), "+f"(d[8]), "+f"(d[9]), "+f"(d[10]), "+f"(d[11]), "+f"(d[12]), "+f"(d[13]), "+f"(d[14]), "+f"(d[15]), "+f"(d[16]), "+f"(d[17]), "+f"(d[18]), "+f"(d[19])
    : "r"(a0), "r"(a1), "r"(a2), "r"(a3), "l"(db), "r"(scale_d), "n"(TB), "n"(SA));
}
template<int TB> __device__ __forceinline__ void wgmma_hrs_n64(uint32_t (&d)[16], uint32_t a0, uint32_t a1, uint32_t a2, uint32_t a3, uint64_t db, int scale_d) {
  asm volatile("{\n.reg .pred p;\nsetp.ne.b32 p, %21, 0;\n"
    "wgmma.mma_async.sync.aligned.m64n64k16.f16.f16.f16 {%0, %1, %2, %3, %4, %5, %6, %7, %8, %9, %10, %11, %12, %13, %14, %15}, {%16, %17, %18, %19}, %20, p, 1, 1, %22;\n}\n"
    : "+r"(d[0]), "+r"(d[1]), "+r"(d[2]), "+r"(d[3]), "+r"(d[4]), "+r"(d[5]), "+r"(d[6]), "+r"(d[7]), "+r"(d[8]), "+r"(d[9]), "+r"(d[10]), "+r"(d[11]), "+r"(d[12]), "+r"(d[13]), "+r"(d[14]), "+r"(d[15])
    : "r"(a0), "r"(a1), "r"(a2), "r"(a3), "l"(db), "r"(scale_d), "n"(TB));
}
template<int TB> __device__ __forceinline__ void wgmma_hrs_n32(uint32_t (&d)[8], uint32_t a0, uint32_t a1, uint32_t a2, uint32_t a3, uint64_t db, int scale_d) {
  asm volatile("{\n.reg .pred p;\nsetp.ne.b32 p, %13, 0;\n"
    "wgmma.mma_async.sync.aligned.m64n32k16.f16.f16.f16 {%0, %1, %2, %3, %4, %5, %6, %7}, {%8, %9, %10, %11}, %12, p, 1, 1, %14;\n}\n"
    : "+r"(d[0]), "+r"(d[1]), "+r"(d[2]), "+r"(d[3]), "+r"(d[4]), "+r"(d[5]), "+r"(d[6]), "+r"(d[7])
    : "r"(a0), "r"(a1), "r"(a2), "r"(a3), "l"(db), "r"(scale_d), "n"(TB));
}

__device__ __align__(128) const uint32_t c_thr[1536] = {
  0x33fb33ff,0xa49c9de4,0x33273352,0xaf2cae76,0x33e233f1,0xa96ca7bd,0x32c432f7,0xb045afdd,0x33b733cf,0xac3eaaf7,0x3250328c,0xb0eab099,
  0x3378339a,0xadbcacff,0x31cd3211,0xb182b137,0x33d033fb,0xaadea46a,0x299e2d17,0xb3e0b396,0x32fb337a,0xafd2adb1,0xa78b1f76,0xb3f2b3ff,
  0x318b3254,0xb1c5b0e5,0xae6bac32,0xb354b3b8,0x2f4230a3,0xb321b285,0xb133b040,0xb215b2c7,0x337c33f2,0xada5a759,0xb179afc8,0xb1d6b2fe,
  0x31463293,0xb204b08e,0xb394b2ba,0xad23b055,0x2b402f4e,0xb3cbb31e,0xb3e4b3f9,0x293ba533,0xac269c52,0xb3bab400,0xb258b357,0x30e02e5f,
  0x330133e5,0xafbda922,0xb3f3b3c9,0x2727ab59,0x2deb314a,0xb36fb200,0xb194b32f,0x31bc2f0a,0xacdb2084,0xb39fb3ff,0xa565aea4,0x33f93347,
  0xb2b6b0db,0xb05ab25c,0x30892c1a,0x329733bc,0x326033d4,0xb0d6aa94,0xb00ab29b,0x32e83084,0x20e82f64,0xb3feb318,0x2d8da597,0x338133f8,
  0xb1fcae48,0xb14fb35c,0x339031b8,0x2d3a3199,0xb3e6b3ae,0x2909ac7b,0x32d133f4,0xb030a6f5,0x319d33bf,0xb1b3ac02,0x2e3ca874,0x335e33ec,
  0xacc32b89,0xb3a3b3c6,0x33f83276,0x25c930b7,0xb3dcb1f8,0xaa01b154,0x30653335,0xb2b0aef4,0xb107b383,0x32392d81,0xafa6214d,0xb307b3fe,
  0x30bc33a5,0xb273acb7,0x33c5311b,0x2ba23229,0xb0cc94b6,0xb267b400,0x30153360,0xb2e1ae31,0xb385b3ab,0x2d76ac93,0xb166a691,0xb1e7b3f5,
  0x22deb06a,0x33fd32ac,0xb337b3da,0x2ee8aa19,0x2f853387,0xb310ad6a,0x322d33fe,0xb1162216,0xb2a9abd3,0xb06fb3c2,0xb07428a6,0xb2a5b3ea,
  0xb111b3e9,0x323128be,0xb30db3c3,0x2f90abba,0x31aa227a,0x31a633fd,0x2e25ad5e,0x33633389,0x2d6a3365,0xb387ae1a,0xa21631aa,0xb3feb1a6,
  0xb3c2af85,0xabd3b310,0xb3eab22d,0x28a6b116,0xa8beb2a9,0x33e9306f,0x2bbab074,0x33c332a5,0x33fd3111,0x227a3231,0x3389330d,0xad5e2f90,
  0x2a63333f,0xb3d7aec6,0xb2a2a1b1,0xb07ab3fe,0xb3f7b158,0x25fbb1f4,0xacb7b38b,0x33a52d52,0x2e0eb025,0x336832d8,0x340030bc,0x14b63273,
  0x323533c0,0xb10c2beb,0xac9330cc,0xb3abb267,0x23433316,0xb3fdaf6f,0xb38eb225,0x2d46b11f,0xb342b29e,0x2ebbb07f,0x31e3aa7c,0x316b33d6,
  0x3264a6c3,0x30d133f5,0x2c0233ac,0xb3bfac87,0x28f0336a,0xb3e7ae02,0xb3c6b19d,0x2b89b1b3,0xa59732e8,0xb3f8b00a,0xaccfb3ed,0x33a1285b,
  0xb1b8b381,0x3199ad8d,0x336c31df,0xadf73170,0x33f42d3a,0x26f53390,0xb30423a7,0xafb2b3fc,0xb05f3030,0xb2b3b2d1,0x29e8b27a,0x33dd30b2,
  0xab5932b6,0xb3c9b05a,0x30adb089,0x327e3297,0xaf0ab3f3,0x332fa727,0x240633b0,0xb3fcac6f,0x33473194,0xaea431bc,0xb174b359,0x31daae54,
  0xb3bca565,0xac1ab3f9,0x33ee2f59,0xa842331b,0xaddf3281,0xb371b0a8,0x34002b40,0x1c5233cb,0xa759b3ef,0x33f22829,0xb2fe2c26,0xafc8b3ba,
  0x308e337c,0xb2932da5,0x3055b179,0x32ba31d6,0xb31eb146,0x2f4eb204,0xa5333394,0xb3f9ad23,0xaff33249,0xb2f1b0f3,0x30e532fb,0xb2542fd2,
  0x2b28b373,0x33cc2dd4,0xb285b18b,0x30a3b1c5,0x246a33fa,0xb3fba500,0x33962f42,0xad173321,0xadb1b3d0,0x337aaade,0xb3ffa99e,0x1f76b3e0,
  0xb0ee320d,0xb24db13c,0xac4b3398,0xb3b5ad0b,0x304ab289,0x32c1309e,0x2985b3ce,0x33e12b0f,0xaf3732f4,0xb324afe8,0xa4ce33f0,0xb3faa7ef,
  0x2dc8b34f,0x33762e82,0x9de4b3ff,0x33ff1ead,0xb1c931cd,0xb186b182,0xb3762e82,0xadc8b34f,0x324db13c,0x30ee320d,0x33b5ad0b,0x2c4b3398,
  0xb2c1309e,0xb04ab289,0xb3e12b0f,0xa985b3ce,0x3324afe8,0x2f3732f4,0x33faa7ef,0x24ce33f0,0xb285318b,0xb0a3b1c5,0xb2c7ae6b,0x3040b354,
  0x3396af42,0x2d173321,0x31413133,0xb2093215,0xb3ff299e,0x9f76b3e0,0xae8db2bd,0x334cb050,0x33b8278b,0xac3233f2,0x281033b3,0xb3ef2c57,
  0xb31e3146,0xaf4eb204,0xa533b394,0x33f9ad23,0x3400ab40,0x9c5233cb,0xae5f33e4,0xb357a93b,0xb2feac26,0x2fc8b3ba,0x3245b258,0x30f830e0,
  0x30553179,0xb2ba31d6,0xb3df2e99,0xa9b6b34a,0xb39230fd,0xad2fb241,0x3200b301,0x314a2fbd,0x337f1b11,0xad993400,0xb3ff2deb,0xa084b36f,
  0xb005b129,0x32ebb21d,0x325c2cdb,0xb0db339f,0xa92233de,0xb3e529cf,0xab59b2b6,0x33c9b05a,0xb3dd30b2,0xa9e8b27a,0x33d4ab71,0xaa9433c8,
  0x32212c0e,0xb12433bd,0xaf64b0d6,0x3318b260,0x197fb345,0x3400aeaf,0xae4833fe,0xb35c20e8,0xb23d3332,0xb102aeff,0x33aeb14f,0x2c7b31fc,
  0xb3fe3065,0xa14db2b0,0x2ebb307f,0xb342329e,0x300f2fa6,0xb2e53307,0x30d1b3f5,0x326426c3,0x302ab400,0x32d517db,0xb3e72e02,0x28f0b36a,
  0xb3fd2f6f,0x2343b316,0x2d46311f,0xb38e3225,0xb3f53015,0x2691b2e1,0xaf9b33eb,0xb30a288d,0x2a193166,0xb3da31e7,0x33d7aec6,0xaa63333f,
  0x3313b337,0x2f7a2ee8,0xa5fbb1f4,0x33f7b158,0xb1a1a8d7,0x31afb3e8,0xb36832d8,0xae0eb025,0xb3c22f85,0x2bd3b310,0xb3ea322d,0xa8a6b116,
  0xa8be32a9,0xb3e9306f,0x2bba3074,0xb3c332a5,0x33fdb111,0xa27a3231,0x3389b30d,0x2d5e2f90,0xa216b1aa,0x33feb1a6,0xaed2ae25,0x333db363,
  0xb3652edd,0x2e1ab33a,0xb1aa227a,0x31a6b3fd,0xaf853387,0xb3102d6a,0xb22d33fe,0xb116a216,0x32a9abd3,0xb06f33c2,0x307428a6,0xb2a533ea,
  0x3111b3e9,0x3231a8be,0x330db3c3,0x2f902bba,0xb2e12e31,0x3015b360,0x288db1a1,0x33ebb1af,0xb1e733f5,0xb1662691,0xb33f2f9b,0x2ec6b30a,
  0x2ee82a19,0xb33733da,0xb15833d7,0xb1f42a63,0x33e8b313,0x28d72f7a,0x302525fb,0xb2d833f7,0xb2392d81,0x3107b383,0x3307b3fe,0x2fa6214d,
  0xb35e33ec,0xae3ca874,0x97dbb00f,0x3400b2e5,0xa5c930b7,0xb3f83276,0xb316302a,0x2f6fb2d5,0x32b0aef4,0xb0653335,0xb29e33fd,0xb07f2343,
  0xb1702ccf,0x31dfb3a1,0x3345b124,0xaeaf3221,0xb3fc336c,0xa3a7adf7,0x3332b400,0x2eff997f,0xb0b23304,0xb27a2fb2,0x2b71b102,0x33c8b23d,
  0x2c0e29e8,0xb3bd33dd,0xb0d62a94,0x3260b3d4,0xb0892c1a,0x3297b3bc,0x2aad2842,0xb3d333ee,0xb3b0327e,0x2c6fb0ad,0x3241b035,0xb0fd32ce,
  0xb35933fc,0xae542406,0x3400b392,0x1b112d2f,0xaf5931da,0xb31b3174,0x321db37f,0x3129ad99,0xaf152ac6,0x332cb3d2,0xb1463293,0xb204308e,
  0xb281312e,0x30a8b219,0xab402f4e,0xb3cb331e,0xb3ef3371,0x2829addf,0x2c269c52,0xb3ba3400,0xb37c33f2,0xada52759,0x3179afc8,0xb1d632fe,
  0xacf32953,0x339cb3e3,0xb3fa33cc,0x2500ab28,0xb0942f21,0x3290b32a,0xb3d033fb,0xaade246a,0xb249317d,0x30f3b1d2,0xb2fb337a,0xafd22db1,
  0xb37332f1,0x2dd4aff3,0xb18b3254,0xb1c530e5,0xa96c27bd,0x33e2b3f1,0xb0452fdd,0x32c4b2f7,0xac3e2af7,0x33b7b3cf,0xb0ea3099,0x3250b28c,
  0xadbc2cff,0x3378b39a,0xb1823137,0x31cdb211,0xaf2c2e76,0x3327b352,0xb20d31c9,0x313cb186,0x313c3186,0xb20db1c9,0x2d0b2dc8,0xb398b376,
  0x309e30ee,0xb289b24d,0x2b0f2c4b,0xb3ceb3b5,0x2fe8304a,0xb2f4b2c1,0x27ef2985,0xb3f0b3e1,0x2e822f37,0xb34fb324,0x1ead24ce,0xb3ffb3fa,
  0xb2bdb209,0xb050b141,0xb290b32a,0x30942f21,0xb3b3b34c,0xac57ae8d,0xb0f3b1d2,0x3249317d,0xb400b3ef,0x1d1ba810,0xadd4aff3,0x337332f1,
  0xb39cb3e3,0x2cf32953,0xa500ab28,0x33fa33cc,0xae99b0f8,0x334a3245,0x33ff33b2,0x201f2c63,0x2438a9b6,0x33fc33df,0x332c33d2,0xaf15aac6,
  0x303a2ce7,0x32cb339e,0x30a83219,0xb281b12e,0x32ee31c0,0x2ffe3190,0x28292ddf,0xb3efb371,0x33b0327e,0x2c6f30ad,0xb241b035,0xb0fdb2ce,
  0x335933fc,0xae54a406,0xb400b392,0x1b11ad2f,0x2f5931da,0xb31bb174,0xb21db37f,0x31292d99,0xaaad2842,0xb3d3b3ee,0xa9cfb005,0x33de32eb,
  0x285b305f,0xb3edb2b3,0x2c0ea9e8,0x33bd33dd,0xb170accf,0xb1dfb3a1,0x33453124,0x2eaf3221,0xb3fcb36c,0x23a7adf7,0x33323400,0xaeff997f,
  0xb0b2b304,0x327a2fb2,0x2b713102,0xb3c8b23d,0xb400b2e5,0x17dbb00f,0x2e023264,0xb36ab0d1,0xaf6fb2d5,0x3316302a,0xb11fa8f0,0xb225b3e7,
  0x307f2343,0x329e33fd,0xb3d6b38e,0x2a7cad46,0x33f53342,0xa6c32ebb,0xac87b1e3,0x33ac316b,0x28d7af7a,0x33e83313,0xb2d8b3f7,0x3025a5fb,
  0x33eb31af,0x288d31a1,0x2bebae0e,0x33c03368,0x2ec6330a,0xb33faf9b,0x33fe3235,0x21b1310c,0xb1f4aa63,0xb158b3d7,0x2d5232a2,0xb38bb07a,
  0x33a7333d,0xacab2ed2,0x33f63162,0x262d31eb,0xaa4b301a,0xb3d8b2de,0x2a32326b,0xb3d9b0c7,0xb3f6b26f,0x265fb0c1,0xb3a9b020,0xac9fb2db,
  0x0e48b15d,0x340031f0,0xae1ab33a,0x33652edd,0xaed22e25,0xb33db363,0xb1eb0e48,0xb162b400,0xb2deb3a7,0x301aacab,0xb0c7b3f6,0x326b262d,
  0x30c1aa4b,0x326f33d8,0x32db2a32,0x302033d9,0x31f033f6,0xb15d265f,0x2edd33a9,0xb33aac9f,0xb2acb385,0x306aad76,0x2a19b166,0x33da31e7,
  0x3229a2de,0x311b33fd,0x33133337,0xaf7a2ee8,0x2e3133c5,0xb360aba2,0xb1a128d7,0xb1afb3e8,0xb3f5b015,0xa691b2e1,0xaf9bb3eb,0x330a288d,
  0x3154acc3,0x31f833a3,0x2ef433f8,0xb335a5c9,0x2d8133dc,0xb383aa01,0xb3feb065,0x214db2b0,0xb3ecb107,0x2874b239,0x300fafa6,0x32e53307,
  0x30b7ae3c,0x3276335e,0x302a3400,0xb2d517db,0x312433bd,0xb2212c0e,0xb318b260,0x2f64b0d6,0xb400aeaf,0x997fb345,0x335c20e8,0x2e4833fe,
  0x3102aeff,0x323d3332,0xac7b31fc,0xb3aeb14f,0x2a9433c8,0xb3d4ab71,0xb084b3e6,0x329ba909,0xb2ce2aad,0xb035b3d3,0x33e529cf,0x292233de,
  0x2d2fb241,0x339230fd,0xb14a2fbd,0xb200b301,0x2d993400,0xb37f1b11,0x2084b36f,0x33ff2deb,0xb2ebb21d,0x3005b129,0x30db339f,0xb25c2cdb,
  0xae5fb3e4,0x3357a93b,0xb190303a,0xb1c0b2cb,0x32453258,0xb0f830e0,0x2c63b2ee,0x33b22ffe,0xb3dfae99,0x29b6b34a,0x2ac633ff,0xb3d2a01f,
  0x339ea438,0x2ce733fc,0xb12eb32c,0x3219af15,0x33b8a78b,0x2c3233f2,0x2810b3b3,0x33ef2c57,0xb2c72e6b,0xb040b354,0x29533400,0xb3e31d1b,
  0x3141b133,0x32093215,0xaf21b39c,0x332aacf3,0xae8d32bd,0xb34cb050,0x317d3290,0xb1d23094,0x27bd33fb,0xb3f1249c,0x2fdd3327,0xb2f72f2c,
  0xaaf7b3e2,0x33cfa96c,0xb099b2c4,0x328cb045,0x2cff33b7,0xb39a2c3e,0x31373250,0xb21130ea,0xae76b378,0x3352adbc,0xb1c9b1cd,0x3186b182,
  0xb3ff1ead,0x1de4b3ff,0xb352adbc,0x2e76b378,0x33f1249c,0xa7bd33fb,0x32f72f2c,0xafdd3327,0xb3cfa96c,0x2af7b3e2,0xb28cb045,0x3099b2c4,
  0x339a2c3e,0xacff33b7,0x321130ea,0xb1373250,0x2953b400,0x33e31d1b,0x33ccadd4,0x2b283373,0xaf21339c,0xb32aacf3,0xb3fb2500,0x246ab3fa,
  0x317db290,0x31d23094,0x337a2ade,0xadb133d0,0xb2f130f3,0xaff3b249,0xb254afd2,0x30e5b2fb,0x339e2438,0xace733fc,0xb12e332c,0xb219af15,
  0xb190b03a,0x31c0b2cb,0x3371b0a8,0x2ddf3281,0x2c6332ee,0xb3b22ffe,0xb3f22829,0x2759b3ef,0x2ac6b3ff,0x33d2a01f,0x32932da5,0xb08e337c,
  0xaf0a33f3,0xb32fa727,0x2406b3b0,0x33fcac6f,0x3347b194,0x2ea431bc,0xb1743359,0xb1daae54,0xb3bc2565,0x2c1ab3f9,0x33eeaf59,0x2842331b,
  0x30ad3089,0xb27e3297,0xb2ceaaad,0x3035b3d3,0xb29ba909,0x3084b3e6,0x305f3030,0xb2b332d1,0x259732e8,0xb3f8300a,0x2ccfb3ed,0x33a1a85b,
  0x31b8b381,0x31992d8d,0xb36c31df,0xadf7b170,0xb3f42d3a,0x26f5b390,0x330423a7,0xafb233fc,0x316bb3d6,0x31e32a7c,0xb3832a01,0x2d81b3dc,
  0xb3bf2c87,0x2c02b3ac,0x28743239,0xb3ec3107,0x2b8931b3,0xb3c6319d,0x3276b35e,0x30b72e3c,0x31f8b3a3,0x31542cc3,0xb33525c9,0x2ef4b3f8,
  0x310c2beb,0xb23533c0,0x33abb267,0x2c9330cc,0x307ab3fe,0x32a2a1b1,0xb06aad76,0x32acb385,0xb3a52d52,0x2cb7b38b,0xb11b33fd,0xb229a2de,
  0x94b63273,0xb40030bc,0x3360aba2,0xae3133c5,0xb2de33a7,0xb01aacab,0xb0c733f6,0xb26b262d,0x30c12a4b,0xb26f33d8,0x32dbaa32,0xb02033d9,
  0x31f0b3f6,0x315d265f,0x2eddb3a9,0x333aac9f,0xb1eb8e48,0x3162b400,0xb3872e1a,0x2d6ab365,0xae25ad5e,0x3363b389,0x8e48b15d,0x3400b1f0,
  0xb3a7333d,0xacabaed2,0xb3f63162,0x262db1eb,0x2a4b301a,0xb3d832de,0xaa32326b,0xb3d930c7,0x33f6b26f,0x265f30c1,0x33a9b020,0xac9f32db,
  0x33c0b368,0x2beb2e0e,0x30cc94b6,0xb2673400,0x21b1b10c,0x33feb235,0x3385b3ab,0x2d762c93,0xb38b307a,0x2d52b2a2,0xa2deb06a,0x33fdb2ac,
  0xb0bc33a5,0xb2732cb7,0xb3c5311b,0x2ba2b229,0x26c32ebb,0xb3f53342,0xb3ac316b,0x2c87b1e3,0x336ab0d1,0xae023264,0xb19d33bf,0xb1b32c02,
  0x3225b3e7,0x311fa8f0,0x2cc32b89,0xb3a333c6,0xaa7cad46,0x33d6b38e,0x33dcb1f8,0xaa013154,0xb3fe3318,0x20e8af64,0x3381b3f8,0x2d8d2597,
  0xb14f335c,0xb1fc2e48,0x2d3ab199,0x3390b1b8,0x29092c7b,0xb3e633ae,0xb03026f5,0x32d1b3f4,0x32e8b084,0xb00a329b,0xb3ed32b3,0x285bb05f,
  0x29cfb005,0x33deb2eb,0xb05a325c,0xb2b630db,0xafbd2922,0x3301b3e5,0x27272b59,0xb3f333c9,0xb36f3200,0x2debb14a,0x31bcaf0a,0xb194332f,
  0xb39f33ff,0xacdba084,0x33f9b347,0xa5652ea4,0x3394b2ba,0xad233055,0xa438a9b6,0x33fcb3df,0x33e4b3f9,0x293b2533,0xb03a2ce7,0x32cbb39e,
  0x3258b357,0x30e0ae5f,0xb2ee31c0,0x2ffeb190,0x2e99b0f8,0x334ab245,0xb3ff33b2,0x201fac63,0xaf4230a3,0xb3213285,0x3133b040,0xb21532c7,
  0xa99e2d17,0xb3e03396,0x32bdb209,0xb0503141,0x278b1f76,0xb3f233ff,0x33b3b34c,0xac572e8d,0x2e6bac32,0xb35433b8,0x3400b3ef,0x1d1b2810,
  0xb289324d,0x309eb0ee,0xb3ce33b5,0x2b0fac4b,0xb2f432c1,0x2fe8b04a,0xb3f033e1,0x27efa985,0xb34f3324,0x2e82af37,0xb3ff33fa,0x1eada4ce,
  0xb3983376,0x2d0badc8,0xb3fb33ff,0xa49c1de4,0x351c35f6,0xac93a617,0xb8a3b93c,0x308d2a16,0x32f43448,0xb160afa5,0xb6a4b7fe,0x353a3389,
  0x2fa53160,0xb448b2f4,0xb389b53a,0x37fe36a4,0x26172c93,0xb5f6b51c,0xaa16b08d,0x393c38a3,0x34c3358c,0xac47a5b2,0xb85fb8f3,0x304229b1,
  0x327e33fd,0xb106af26,0xb63cb785,0x34e7330f,0x2f263106,0xb3fdb27e,0xb30fb4e7,0x3785363c,0x25b22c47,0xb58cb4c3,0xa9b1b042,0x38f3385f,
  0x346a3523,0xabf6a54d,0xb81ab8a8,0x2fef294d,0x3209336b,0xb0acaea7,0xb5d4b70a,0x34933294,0x2ea730ac,0xb36bb209,0xb294b493,0x370a35d4,
  0x254d2bf6,0xb523b46a,0xa94dafef,0x38a8381a,0x341334bc,0xab5fa4e9,0xb7a6b85a,0x2f5928e8,0x319432da,0xb052ae28,0xb56ab68d,0x343e3219,
  0x2e283052,0xb2dab194,0xb219b43e,0x368d356a,0x24e92b5f,0xb4bcb413,0xa8e8af59,0x385a37a6,0x33783456,0xaac8a484,0xb715b80a,0x2ec32884,
  0x3120324a,0xaff2ada9,0xb4ffb60e,0x33d3319e,0x2da92ff2,0xb24ab120,0xb19eb3d3,0x360e34ff,0x24842ac8,0xb456b378,0xa884aec3,0x380a3715,
  0x32cd33e3,0xaa31a420,0xb682b76f,0x2e2d281f,0x30ac31bb,0xaf3fad2a,0xb493b58d,0x33283122,0x2d2a2f3f,0xb1bbb0ac,0xb122b328,0x358d3493,
  0x24202a31,0xb3e3b2cd,0xa81fae2d,0x376f3682,0x3223331c,0xa999a376,0xb5ebb6c6,0x2d972776,0x3039312d,0xae8dacac,0xb426b50b,0x327c30a6,
  0x2cac2e8d,0xb12db039,0xb0a6b27c,0x350b3426,0x23762999,0xb31cb223,0xa776ad97,0x36c635eb,0x317a3257,0xa902a2ad,0xb552b61a,0x2d0026ad,
  0x2f8c309f,0xaddcac2e,0xb371b487,0x31cf3029,0x2c2e2ddc,0xb09faf8c,0xb029b1cf,0x34873371,0x22ad2902,0xb257b17a,0xa6adad00,0x361a3552,
  0x30d23194,0xa86ba1e4,0xb4b7b56a,0x2c6a25e4,0x2ea73012,0xad2aab5f,0xb294b402,0x31222f59,0x2b5f2d2a,0xb012aea7,0xaf59b122,0x34023294,
  0x21e4286b,0xb194b0d2,0xa5e4ac6a,0x356a34b7,0x302c30d2,0xa7a9a11b,0xb41ab4b7,0x2ba7251b,0x2dc22f0c,0xac79aa63,0xb1b6b2f7,0x30742e5f,
  0x2a632c79,0xaf0cadc2,0xae5fb074,0x32f731b6,0x211b27a9,0xb0d2b02c,0xa51baba7,0x34b7341a,0x2f0c3012,0xa67ba052,0xb2f7b402,0x2a7a2452,
  0x2cde2df5,0xab91a967,0xb0d7b1e8,0x2f8b2d65,0x29672b91,0xadf5acde,0xad65af8b,0x31e830d7,0x2052267b,0xb012af0c,0xa452aa7a,0x340232f7,
  0x2dc22ea7,0xa54d9f12,0xb1b6b294,0x294d2311,0x2bf62cde,0xaa31a86b,0xafefb0d7,0x2e2d2c6a,0x286b2a31,0xacdeabf6,0xac6aae2d,0x30d72fef,
  0x1f12254d,0xaea7adc2,0xa311a94d,0x329431b6,0x2c792d2a,0xa4209d7f,0xb074b122,0x281f217f,0x2a312b91,0xa8d0a6e0,0xae2daf8b,0x2cce2ade,
  0x26e028d0,0xab91aa31,0xaadeacce,0x2f8b2e2d,0x1d7f2420,0xad2aac79,0xa17fa81f,0x31223074,0x2a632b5f,0xa1e49bdb,0xae5faf59,0x25e41fdb,
  0x286b2967,0xa6e0a4e9,0xac6aad65,0x2ade28e8,0x24e926e0,0xa967a86b,0xa8e8aade,0x2d652c6a,0x1bdb21e4,0xab5faa63,0x9fdba5e4,0x2f592e5f,
  0x27a9286b,0x9f1298b6,0xaba7ac6a,0x23111cb6,0x254d267b,0xa420a1e4,0xa94daa7a,0x281f25e4,0x21e42420,0xa67ba54d,0xa5e4a81f,0x2a7a294d,
  0x18b61f12,0xa86ba7a9,0x9cb6a311,0x2c6a2ba7,0x211b21e4,0x98b69248,0xa51ba5e4,0x1cb61648,0x1f122052,0x9d7f9bdb,0xa311a452,0x217f1fdb,
  0x1bdb1d7f,0xa0529f12,0x9fdba17f,0x24522311,0x124818b6,0xa1e4a11b,0x96489cb6,0x25e4251b,0xa11ba1e4,0x18b61248,0x251b25e4,0x9cb69648,
  0x9f12a052,0x1d7f1bdb,0x23112452,0xa17f9fdb,0x9bdb9d7f,0x20521f12,0x1fdb217f,0xa452a311,0x924898b6,0x21e4211b,0x16481cb6,0xa5e4a51b,
  0xa7a9a86b,0x1f1218b6,0x2ba72c6a,0xa3119cb6,0xa54da67b,0x242021e4,0x294d2a7a,0xa81fa5e4,0xa1e4a420,0x267b254d,0x25e4281f,0xaa7aa94d,
  0x98b69f12,0x286b27a9,0x1cb62311,0xac6aaba7,0xaa63ab5f,0x21e41bdb,0x2e5f2f59,0xa5e49fdb,0xa86ba967,0x26e024e9,0x2c6a2d65,0xaadea8e8,
  0xa4e9a6e0,0x2967286b,0x28e82ade,0xad65ac6a,0x9bdba1e4,0x2b5f2a63,0x1fdb25e4,0xaf59ae5f,0xac79ad2a,0x24201d7f,0x30743122,0xa81fa17f,
  0xaa31ab91,0x28d026e0,0x2e2d2f8b,0xacceaade,0xa6e0a8d0,0x2b912a31,0x2ade2cce,0xaf8bae2d,0x9d7fa420,0x2d2a2c79,0x217f281f,0xb122b074,
  0xadc2aea7,0x254d1f12,0x31b63294,0xa94da311,0xabf6acde,0x2a31286b,0x2fef30d7,0xae2dac6a,0xa86baa31,0x2cde2bf6,0x2c6a2e2d,0xb0d7afef,
  0x9f12a54d,0x2ea72dc2,0x2311294d,0xb294b1b6,0xaf0cb012,0x267b2052,0x32f73402,0xaa7aa452,0xacdeadf5,0x2b912967,0x30d731e8,0xaf8bad65,
  0xa967ab91,0x2df52cde,0x2d652f8b,0xb1e8b0d7,0xa052a67b,0x30122f0c,0x24522a7a,0xb402b2f7,0xb02cb0d2,0x27a9211b,0x341a34b7,0xaba7a51b,
  0xadc2af0c,0x2c792a63,0x31b632f7,0xb074ae5f,0xaa63ac79,0x2f0c2dc2,0x2e5f3074,0xb2f7b1b6,0xa11ba7a9,0x30d2302c,0x251b2ba7,0xb4b7b41a,
  0xb0d2b194,0x286b21e4,0x34b7356a,0xac6aa5e4,0xaea7b012,0x2d2a2b5f,0x32943402,0xb122af59,0xab5fad2a,0x30122ea7,0x2f593122,0xb402b294,
  0xa1e4a86b,0x319430d2,0x25e42c6a,0xb56ab4b7,0xb17ab257,0x290222ad,0x3552361a,0xad00a6ad,0xaf8cb09f,0x2ddc2c2e,0x33713487,0xb1cfb029,
  0xac2eaddc,0x309f2f8c,0x302931cf,0xb487b371,0xa2ada902,0x3257317a,0x26ad2d00,0xb61ab552,0xb223b31c,0x29992376,0x35eb36c6,0xad97a776,
  0xb039b12d,0x2e8d2cac,0x3426350b,0xb27cb0a6,0xacacae8d,0x312d3039,0x30a6327c,0xb50bb426,0xa376a999,0x331c3223,0x27762d97,0xb6c6b5eb,
  0xb2cdb3e3,0x2a312420,0x3682376f,0xae2da81f,0xb0acb1bb,0x2f3f2d2a,0x3493358d,0xb328b122,0xad2aaf3f,0x31bb30ac,0x31223328,0xb58db493,
  0xa420aa31,0x33e332cd,0x281f2e2d,0xb76fb682,0xb378b456,0x2ac82484,0x3715380a,0xaec3a884,0xb120b24a,0x2ff22da9,0x34ff360e,0xb3d3b19e,
  0xada9aff2,0x324a3120,0x319e33d3,0xb60eb4ff,0xa484aac8,0x34563378,0x28842ec3,0xb80ab715,0xb413b4bc,0x2b5f24e9,0x37a6385a,0xaf59a8e8,
  0xb194b2da,0x30522e28,0x356a368d,0xb43eb219,0xae28b052,0x32da3194,0x3219343e,0xb68db56a,0xa4e9ab5f,0x34bc3413,0x28e82f59,0xb85ab7a6,
  0xb46ab523,0x2bf6254d,0x381a38a8,0xafefa94d,0xb209b36b,0x30ac2ea7,0x35d4370a,0xb493b294,0xaea7b0ac,0x336b3209,0x32943493,0xb70ab5d4,
  0xa54dabf6,0x3523346a,0x294d2fef,0xb8a8b81a,0xb4c3b58c,0x2c4725b2,0x385f38f3,0xb042a9b1,0xb27eb3fd,0x31062f26,0x363c3785,0xb4e7b30f,
  0xaf26b106,0x33fd327e,0x330f34e7,0xb785b63c,0xa5b2ac47,0x358c34c3,0x29b13042,0xb8f3b85f,0xb51cb5f6,0x2c932617,0x38a3393c,0xb08daa16,
  0xb2f4b448,0x31602fa5,0x36a437fe,0xb53ab389,0xafa5b160,0x344832f4,0x3389353a,0xb7feb6a4,0xa617ac93,0x35f6351c,0x2a16308d,0xb93cb8a3,
};
__device__ __align__(128) const uint32_t c_img[2560] = {
  0x326d31ed,0x333b32dd,0x33c33388,0x33fe33ea,0x33c331ed,0x31ed33c3,0xa8b22d64,0xb33bb0c4,0x33ea31ed,0xad64301d,0xb2ddb388,0x315fa8b2,
  0x32dd31ed,0xb3feabc6,0x326dad64,0xad64326d,0x30c431ed,0xaed7b2dd,0x2bc63388,0xa248b3ea,0x2bc631ed,0x315fb3c3,0xb3ea2d64,0x2ed730c4,
  0xa8b231ed,0x3388b01d,0x301db388,0xb1ed28b2,0xb01d31ed,0x22482bc6,0x30c4ad64,0x3388b26d,0x33ea33fe,0x338833c3,0x32dd333b,0x31ed326d,
  0xb2ddb3fe,0xa248b01d,0x326d2ed7,0x338833ea,0x30c433fe,0xb33babc6,0xabc6b33b,0x33fe30c4,0xabc6b3fe,0x31ed32dd,0xb3eaaed7,0x333ba8b2,
  0xa8b233fe,0x2d64b3c3,0xb01d333b,0x315fb26d,0x301db3fe,0xb3fe301d,0x30c42ed7,0x2d64b3ea,0xb26d33fe,0x2ed72bc6,0x33c3b33b,0xa248b0c4,
  0x33c3b3fe,0x315fb2dd,0x28b2aed7,0xaed728b2,0xb0c4b15f,0xaed7b01d,0xabc6ad64,0xa248a8b2,0xabc6b15f,0x315f2bc6,0x33ea3388,0x2ed7326d,
  0x28b2b15f,0x338832dd,0xb01d2d64,0xb1edb3ea,0x301db15f,0x224833c3,0xb0c4b388,0x338830c4,0x326db15f,0xb33b301d,0x33c3ad64,0xb3fe28b2,
  0x33c3b15f,0xb1edabc6,0xa8b23388,0x333bb26d,0x33eab15f,0x2d64b2dd,0xb2dd2d64,0xb15f33ea,0x32ddb15f,0x33feb3c3,0x326db388,0x2d64b0c4,
  0x28b22248,0x2d642bc6,0x301d2ed7,0x315f30c4,0xb01da248,0xb3feb2dd,0xb0c4b33b,0x2d64a8b2,0x326d2248,0x2ed733c3,0xb3c3aed7,0xa248b26d,
  0xb3c3a248,0x315fb01d,0xa8b2333b,0xaed7b3ea,0x33ea2248,0xb388abc6,0x32dd2ed7,0xb1edb0c4,0xb2dda248,0x224832dd,0x326db33b,0xb38828b2,
  0x30c42248,0x333bb3c3,0xabc6aed7,0xb3fe326d,0xabc6a248,0xb1ed301d,0xb3ea333b,0xb33b33ea,0xb26d31ed,0xb33b32dd,0xb3c33388,0xb3fe33ea,
  0xb3c331ed,0xb1ed33c3,0x28b22d64,0x333bb0c4,0xb3ea31ed,0x2d64301d,0x32ddb388,0xb15fa8b2,0xb2dd31ed,0x33feabc6,0xb26dad64,0x2d64326d,
  0xb0c431ed,0x2ed7b2dd,0xabc63388,0x2248b3ea,0xabc631ed,0xb15fb3c3,0x33ea2d64,0xaed730c4,0x28b231ed,0xb388b01d,0xb01db388,0x31ed28b2,
  0x301d31ed,0xa2482bc6,0xb0c4ad64,0xb388b26d,0xb3ea33fe,0xb38833c3,0xb2dd333b,0xb1ed326d,0x32ddb3fe,0x2248b01d,0xb26d2ed7,0xb38833ea,
  0xb0c433fe,0x333babc6,0x2bc6b33b,0xb3fe30c4,0x2bc6b3fe,0xb1ed32dd,0x33eaaed7,0xb33ba8b2,0x28b233fe,0xad64b3c3,0x301d333b,0xb15fb26d,
  0xb01db3fe,0x33fe301d,0xb0c42ed7,0xad64b3ea,0x326d33fe,0xaed72bc6,0xb3c3b33b,0x2248b0c4,0xb3c3b3fe,0xb15fb2dd,0xa8b2aed7,0x2ed728b2,
  0x30c4b15f,0x2ed7b01d,0x2bc6ad64,0x2248a8b2,0x2bc6b15f,0xb15f2bc6,0xb3ea3388,0xaed7326d,0xa8b2b15f,0xb38832dd,0x301d2d64,0x31edb3ea,
  0xb01db15f,0xa24833c3,0x30c4b388,0xb38830c4,0xb26db15f,0x333b301d,0xb3c3ad64,0x33fe28b2,0xb3c3b15f,0x31edabc6,0x28b23388,0xb33bb26d,
  0xb3eab15f,0xad64b2dd,0x32dd2d64,0x315f33ea,0xb2ddb15f,0xb3feb3c3,0xb26db388,0xad64b0c4,0xa8b22248,0xad642bc6,0xb01d2ed7,0xb15f30c4,
  0x301da248,0x33feb2dd,0x30c4b33b,0xad64a8b2,0xb26d2248,0xaed733c3,0x33c3aed7,0x2248b26d,0x33c3a248,0xb15fb01d,0x28b2333b,0x2ed7b3ea,
  0xb3ea2248,0x3388abc6,0xb2dd2ed7,0x31edb0c4,0x32dda248,0xa24832dd,0xb26db33b,0x338828b2,0xb0c42248,0xb33bb3c3,0x2bc6aed7,0x33fe326d,
  0x2bc6a248,0x31ed301d,0x33ea333b,0x333b33ea,0x30c4315f,0x2ed7301d,0x2bc62d64,0x224828b2,0x2bc6315f,0xb15fabc6,0xb3eab388,0xaed7b26d,
  0xa8b2315f,0xb388b2dd,0x301dad64,0x31ed33ea,0xb01d315f,0xa248b3c3,0x30c43388,0xb388b0c4,0xb26d315f,0x333bb01d,0xb3c32d64,0x33fea8b2,
  0xb3c3315f,0x31ed2bc6,0x28b2b388,0xb33b326d,0xb3ea315f,0xad6432dd,0x32ddad64,0x315fb3ea,0xb2dd315f,0xb3fe33c3,0xb26d3388,0xad6430c4,
  0xa8b2a248,0xad64abc6,0xb01daed7,0xb15fb0c4,0x301d2248,0x33fe32dd,0x30c4333b,0xad6428b2,0xb26da248,0xaed7b3c3,0x33c32ed7,0x2248326d,
  0x33c32248,0xb15f301d,0x28b2b33b,0x2ed733ea,0xb3eaa248,0x33882bc6,0xb2ddaed7,0x31ed30c4,0x32dd2248,0xa248b2dd,0xb26d333b,0x3388a8b2,
  0xb0c4a248,0xb33b33c3,0x2bc62ed7,0x33feb26d,0x2bc62248,0x31edb01d,0x33eab33b,0x333bb3ea,0x326d31ed,0x333b32dd,0x33c33388,0x33fe33ea,
  0x33c331ed,0x31ed33c3,0xa8b22d64,0xb33bb0c4,0x33ea31ed,0xad64301d,0xb2ddb388,0x315fa8b2,0x32dd31ed,0xb3feabc6,0x326dad64,0xad64326d,
  0x30c431ed,0xaed7b2dd,0x2bc63388,0xa248b3ea,0x2bc631ed,0x315fb3c3,0xb3ea2d64,0x2ed730c4,0xa8b231ed,0x3388b01d,0x301db388,0xb1ed28b2,
  0xb01d31ed,0x22482bc6,0x30c4ad64,0x3388b26d,0x33ea33fe,0x338833c3,0x32dd333b,0x31ed326d,0xb2ddb3fe,0xa248b01d,0x326d2ed7,0x338833ea,
  0x30c433fe,0xb33babc6,0xabc6b33b,0x33fe30c4,0xabc6b3fe,0x31ed32dd,0xb3eaaed7,0x333ba8b2,0xa8b233fe,0x2d64b3c3,0xb01d333b,0x315fb26d,
  0x301db3fe,0xb3fe301d,0x30c42ed7,0x2d64b3ea,0xb26d33fe,0x2ed72bc6,0x33c3b33b,0xa248b0c4,0x33c3b3fe,0x315fb2dd,0x28b2aed7,0xaed728b2,
  0xb0c4315f,0xaed7301d,0xabc62d64,0xa24828b2,0xabc6315f,0x315fabc6,0x33eab388,0x2ed7b26d,0x28b2315f,0x3388b2dd,0xb01dad64,0xb1ed33ea,
  0x301d315f,0x2248b3c3,0xb0c43388,0x3388b0c4,0x326d315f,0xb33bb01d,0x33c32d64,0xb3fea8b2,0x33c3315f,0xb1ed2bc6,0xa8b2b388,0x333b326d,
  0x33ea315f,0x2d6432dd,0xb2ddad64,0xb15fb3ea,0x32dd315f,0x33fe33c3,0x326d3388,0x2d6430c4,0x28b2a248,0x2d64abc6,0x301daed7,0x315fb0c4,
  0xb01d2248,0xb3fe32dd,0xb0c4333b,0x2d6428b2,0x326da248,0x2ed7b3c3,0xb3c32ed7,0xa248326d,0xb3c32248,0x315f301d,0xa8b2b33b,0xaed733ea,
  0x33eaa248,0xb3882bc6,0x32ddaed7,0xb1ed30c4,0xb2dd2248,0x2248b2dd,0x326d333b,0xb388a8b2,0x30c4a248,0x333b33c3,0xabc62ed7,0xb3feb26d,
  0xabc62248,0xb1edb01d,0xb3eab33b,0xb33bb3ea,0xb26d31ed,0xb33b32dd,0xb3c33388,0xb3fe33ea,0xb3c331ed,0xb1ed33c3,0x28b22d64,0x333bb0c4,
  0xb3ea31ed,0x2d64301d,0x32ddb388,0xb15fa8b2,0xb2dd31ed,0x33feabc6,0xb26dad64,0x2d64326d,0xb0c431ed,0x2ed7b2dd,0xabc63388,0x2248b3ea,
  0xabc631ed,0xb15fb3c3,0x33ea2d64,0xaed730c4,0x28b231ed,0xb388b01d,0xb01db388,0x31ed28b2,0x301d31ed,0xa2482bc6,0xb0c4ad64,0xb388b26d,
  0xb3ea33fe,0xb38833c3,0xb2dd333b,0xb1ed326d,0x32ddb3fe,0x2248b01d,0xb26d2ed7,0xb38833ea,0xb0c433fe,0x333babc6,0x2bc6b33b,0xb3fe30c4,
  0x2bc6b3fe,0xb1ed32dd,0x33eaaed7,0xb33ba8b2,0x28b233fe,0xad64b3c3,0x301d333b,0xb15fb26d,0xb01db3fe,0x33fe301d,0xb0c42ed7,0xad64b3ea,
  0x326d33fe,0xaed72bc6,0xb3c3b33b,0x2248b0c4,0xb3c3b3fe,0xb15fb2dd,0xa8b2aed7,0x2ed728b2,0x29ed29ed,0x29ed29ed,0x29ed29ed,0x29ed29ed,
  0x2bc32a6d,0x2add2bea,0x23c628c4,0xa81da0b2,0x2bc32add,0xa3c6281d,0xabc3aadd,0x23c6a81d,0x29ed2b3b,0xabfea564,0x295fa6d7,0x1a482b88,
  0x25642b88,0xa564ab88,0x25642b88,0xa564ab88,0xa0b22bc3,0x2a6daadd,0xabea23c6,0x28c4281d,0xa8c42bea,0x2a6da0b2,0x28c4abea,0xaa6d20b2,
  0xab3b2bfe,0xa564295f,0x26d79a48,0x2b88a9ed,0x29ed29ed,0x29ed29ed,0x29ed29ed,0x29ed29ed,0xabc3aa6d,0xaaddabea,0xa3c6a8c4,0x281d20b2,
  0x2bc32add,0xa3c6281d,0xabc3aadd,0x23c6a81d,0xa9edab3b,0x2bfe2564,0xa95f26d7,0x9a48ab88,0x25642b88,0xa564ab88,0x25642b88,0xa564ab88,
  0x20b2abc3,0xaa6d2add,0x2beaa3c6,0xa8c4a81d,0xa8c42bea,0x2a6da0b2,0x28c4abea,0xaa6d20b2,0x2b3babfe,0x2564a95f,0xa6d71a48,0xab8829ed,
  0x295f295f,0x295f295f,0x295f295f,0x295f295f,0x23c628c4,0xa81da0b2,0xabc3aa6d,0xaaddabea,0xa3c6281d,0xabc3aadd,0x23c6a81d,0x2bc32add,
  0xa95f26d7,0x9a48ab88,0x29ed2b3b,0xabfea564,0xab882564,0x2b88a564,0xab882564,0x2b88a564,0xabea23c6,0x28c4281d,0x20b2abc3,0xaa6d2add,
  0xaa6d20b2,0xa8c42bea,0x2a6da0b2,0x28c4abea,0xa6d71a48,0xab8829ed,0xab3b2bfe,0xa564295f,0x295f295f,0x295f295f,0x295f295f,0x295f295f,
  0xa3c6a8c4,0x281d20b2,0x2bc32a6d,0x2add2bea,0xa3c6281d,0xabc3aadd,0x23c6a81d,0x2bc32add,0x295fa6d7,0x1a482b88,0xa9edab3b,0x2bfe2564,
  0xab882564,0x2b88a564,0xab882564,0x2b88a564,0x2beaa3c6,0xa8c4a81d,0xa0b22bc3,0x2a6daadd,0xaa6d20b2,0xa8c42bea,0x2a6da0b2,0x28c4abea,
  0x26d79a48,0x2b88a9ed,0x2b3babfe,0x2564a95f,0xabfe2bfe,0xabfe2bfe,0xabfe2bfe,0xabfe2bfe,0xaadd2bea,0xa3c628c4,0x281da0b2,0x2bc3aa6d,
  0xa81d2bc3,0x2adda3c6,0x281dabc3,0xaadd23c6,0x9a482b88,0x29edab3b,0xabfe2564,0x295f26d7,0x26d72b3b,0xa6d7ab3b,0x26d72b3b,0xa6d7ab3b,
  0x2a6d2add,0xabeaa3c6,0x28c4a81d,0x20b22bc3,0x2bea2a6d,0xa0b228c4,0xabeaaa6d,0x20b2a8c4,0x2b8829ed,0x2b3b2bfe,0x2564295f,0xa6d79a48,
  0xabfe2bfe,0xabfe2bfe,0xabfe2bfe,0xabfe2bfe,0x2addabea,0x23c6a8c4,0xa81d20b2,0xabc32a6d,0xa81d2bc3,0x2adda3c6,0x281dabc3,0xaadd23c6,
  0x1a48ab88,0xa9ed2b3b,0x2bfea564,0xa95fa6d7,0x26d72b3b,0xa6d7ab3b,0x26d72b3b,0xa6d7ab3b,0xaa6daadd,0x2bea23c6,0xa8c4281d,0xa0b2abc3,
  0x2bea2a6d,0xa0b228c4,0xabeaaa6d,0x20b2a8c4,0xab88a9ed,0xab3babfe,0xa564a95f,0x26d71a48,0x1a489a48,0x1a489a48,0x1a489a48,0x1a489a48,
  0x281da0b2,0x2bc3aa6d,0x2addabea,0x23c6a8c4,0x2adda3c6,0x281dabc3,0xaadd23c6,0xa81d2bc3,0x2bfea564,0xa95fa6d7,0x9a482b88,0x29edab3b,
  0x2b3ba6d7,0xab3b26d7,0x2b3ba6d7,0xab3b26d7,0x28c4a81d,0x20b22bc3,0xaa6daadd,0x2bea23c6,0x20b2a8c4,0x2bea2a6d,0xa0b228c4,0xabeaaa6d,
  0xa564a95f,0x26d71a48,0x2b8829ed,0x2b3b2bfe,0x1a489a48,0x1a489a48,0x1a489a48,0x1a489a48,0xa81d20b2,0xabc32a6d,0xaadd2bea,0xa3c628c4,
  0x2adda3c6,0x281dabc3,0xaadd23c6,0xa81d2bc3,0xabfe2564,0x295f26d7,0x1a48ab88,0xa9ed2b3b,0x2b3ba6d7,0xab3b26d7,0x2b3ba6d7,0xab3b26d7,
  0xa8c4281d,0xa0b2abc3,0x2a6d2add,0xabeaa3c6,0x20b2a8c4,0x2bea2a6d,0xa0b228c4,0xabeaaa6d,0x2564295f,0xa6d79a48,0xab88a9ed,0xab3babfe,
  0xa95fa95f,0xa95fa95f,0xa95fa95f,0xa95fa95f,0xa3c6a8c4,0x281d20b2,0x2bc32a6d,0x2add2bea,0x23c6a81d,0x2bc32add,0xa3c6281d,0xabc3aadd,
  0x295fa6d7,0x1a482b88,0xa9edab3b,0x2bfe2564,0x2b88a564,0xab882564,0x2b88a564,0xab882564,0x2beaa3c6,0xa8c4a81d,0xa0b22bc3,0x2a6daadd,
  0x2a6da0b2,0x28c4abea,0xaa6d20b2,0xa8c42bea,0x26d79a48,0x2b88a9ed,0x2b3babfe,0x2564a95f,0xa95fa95f,0xa95fa95f,0xa95fa95f,0xa95fa95f,
  0x23c628c4,0xa81da0b2,0xabc3aa6d,0xaaddabea,0x23c6a81d,0x2bc32add,0xa3c6281d,0xabc3aadd,0xa95f26d7,0x9a48ab88,0x29ed2b3b,0xabfea564,
  0x2b88a564,0xab882564,0x2b88a564,0xab882564,0xabea23c6,0x28c4281d,0x20b2abc3,0xaa6d2add,0x2a6da0b2,0x28c4abea,0xaa6d20b2,0xa8c42bea,
  0xa6d71a48,0xab8829ed,0xab3b2bfe,0xa564295f,0x29ed29ed,0x29ed29ed,0x29ed29ed,0x29ed29ed,0x2bc32a6d,0x2add2bea,0x23c628c4,0xa81da0b2,
  0x2bc32add,0xa3c6281d,0xabc3aadd,0x23c6a81d,0x29ed2b3b,0xabfea564,0x295fa6d7,0x1a482b88,0x25642b88,0xa564ab88,0x25642b88,0xa564ab88,
  0xa0b22bc3,0x2a6daadd,0xabea23c6,0x28c4281d,0xa8c42bea,0x2a6da0b2,0x28c4abea,0xaa6d20b2,0xab3b2bfe,0xa564295f,0x26d79a48,0x2b88a9ed,
  0x29ed29ed,0x29ed29ed,0x29ed29ed,0x29ed29ed,0xabc3aa6d,0xaaddabea,0xa3c6a8c4,0x281d20b2,0x2bc32add,0xa3c6281d,0xabc3aadd,0x23c6a81d,
  0xa9edab3b,0x2bfe2564,0xa95f26d7,0x9a48ab88,0x25642b88,0xa564ab88,0x25642b88,0xa564ab88,0x20b2abc3,0xaa6d2add,0x2beaa3c6,0xa8c4a81d,
  0xa8c42bea,0x2a6da0b2,0x28c4abea,0xaa6d20b2,0x2b3babfe,0x2564a95f,0xa6d71a48,0xab8829ed,0x9a481a48,0x9a481a48,0x9a481a48,0x9a481a48,
  0xa81d20b2,0xabc32a6d,0xaadd2bea,0xa3c628c4,0xaadd23c6,0xa81d2bc3,0x2adda3c6,0x281dabc3,0xabfe2564,0x295f26d7,0x1a48ab88,0xa9ed2b3b,
  0xab3b26d7,0x2b3ba6d7,0xab3b26d7,0x2b3ba6d7,0xa8c4281d,0xa0b2abc3,0x2a6d2add,0xabeaa3c6,0xa0b228c4,0xabeaaa6d,0x20b2a8c4,0x2bea2a6d,
  0x2564295f,0xa6d79a48,0xab88a9ed,0xab3babfe,0x9a481a48,0x9a481a48,0x9a481a48,0x9a481a48,0x281da0b2,0x2bc3aa6d,0x2addabea,0x23c6a8c4,
  0xaadd23c6,0xa81d2bc3,0x2adda3c6,0x281dabc3,0x2bfea564,0xa95fa6d7,0x9a482b88,0x29edab3b,0xab3b26d7,0x2b3ba6d7,0xab3b26d7,0x2b3ba6d7,
  0x28c4a81d,0x20b22bc3,0xaa6daadd,0x2bea23c6,0xa0b228c4,0xabeaaa6d,0x20b2a8c4,0x2bea2a6d,0xa564a95f,0x26d71a48,0x2b8829ed,0x2b3b2bfe,
  0xabfe2bfe,0xabfe2bfe,0xabfe2bfe,0xabfe2bfe,0xaadd2bea,0xa3c628c4,0x281da0b2,0x2bc3aa6d,0xa81d2bc3,0x2adda3c6,0x281dabc3,0xaadd23c6,
  0x9a482b88,0x29edab3b,0xabfe2564,0x295f26d7,0x26d72b3b,0xa6d7ab3b,0x26d72b3b,0xa6d7ab3b,0x2a6d2add,0xabeaa3c6,0x28c4a81d,0x20b22bc3,
  0x2bea2a6d,0xa0b228c4,0xabeaaa6d,0x20b2a8c4,0x2b8829ed,0x2b3b2bfe,0x2564295f,0xa6d79a48,0xabfe2bfe,0xabfe2bfe,0xabfe2bfe,0xabfe2bfe,
  0x2addabea,0x23c6a8c4,0xa81d20b2,0xabc32a6d,0xa81d2bc3,0x2adda3c6,0x281dabc3,0xaadd23c6,0x1a48ab88,0xa9ed2b3b,0x2bfea564,0xa95fa6d7,
  0x26d72b3b,0xa6d7ab3b,0x26d72b3b,0xa6d7ab3b,0xaa6daadd,0x2bea23c6,0xa8c4281d,0xa0b2abc3,0x2bea2a6d,0xa0b228c4,0xabeaaa6d,0x20b2a8c4,
  0xab88a9ed,0xab3babfe,0xa564a95f,0x26d71a48,0x3bfb3bff,0x3be53bf2,0x3bbf3bd4,0x3b873ba5,0x3bd03bfb,0x3b013b7c,0x399d3a60,0x378538bc,
  0x35173b52,0xbbc9b7c8,0xb074ba9b,0x3bfe391b,0x319e3b27,0xbbf3b979,0x363cb80a,0x3a2d3bc5,0xba093986,0x3a7eb8f8,0xbae5385f,0x3b3db77a,
  0xbabd393c,0x3bb0b699,0xbc00305b,0x3ba730d7,0xbb2a35c8,0xb8353bb2,0x3a64b1e8,0x3962bbf7,0xba90350b,0xba413bff,0x3602340e,0x3bf6bad8,
  0xac6aa5e4,0xb122af59,0xb402b294,0xb56ab4b7,0xb2deac9c,0xb7bdb5a5,0xb9b3b8d6,0xbb10ba73,0xbb96b676,0xb359bafe,0x3bec3884,0x2a163a29,
  0xbbe0b72c,0x2f27b9d6,0x3b5e3ae8,0xb91633a2,0xb941b9c9,0x38ad3a45,0xb80fbab3,0x36d23b13,0xb850ba0d,0x346f3b4a,0x1fdbbbed,0xb4ab3be8,
  0x3721bb76,0xbace3463,0xb8d13bdd,0x39ebadfb,0x3894bb98,0xb8fd281f,0xbb6a3bbd,0x2e2d3825,0x3b3f3b65,0x3ae83b16,0x3a813ab6,0x3a0d3a49,
  0x3263356a,0xad972b43,0xb5dfb359,0xb8eeb7f3,0xa9b139aa,0xbbedba25,0x3340b889,0x3b983afb,0xbaa2aa16,0xb4cfbb8e,0x3c0038ad,0xb44b38e5,
  0xbb853625,0x3bbdb4c3,0xbbe432ad,0x3bfbaf8b,0xbaacb6d2,0x39243954,0xb65fbace,0x2fbd3bb8,0xb9661648,0xba603bf8,0x383a31cf,0x3b27bbb3,
  0x3219b9eb,0xbb1836f4,0xb9903be5,0x37dd3010,0xb6c6b61a,0xb80ab76f,0xb8a8b85a,0xb93cb8f3,0xbbd7bb87,0xbbf8bbfd,0xbb71bbc9,0xba4dbaf1,
  0xbbfeb9a6,0x305bb91f,0x3bcb3a97,0xb50b37d2,0xb87abbfe,0x3ba13546,0x24523a7e,0xbbb5ba54,0xb576bb63,0x340e3ba3,0xb13bbbd3,0x2c9c3bf2,
  0x386abb3d,0xba2139f8,0x3b57b835,0xbbf13432,0x39e7bc00,0xb8d6adc9,0xbacb3bde,0x372c3457,0x3bdab962,0x3764bb35,0xb9c03122,0xbaf73bef,
  0x398b39cd,0x38fd3946,0x386538b2,0x37853815,0xba85b9c9,0xbb92bb1e,0xbbfebbdd,0xbbc2bbf5,0xb66b3682,0xbb01bb94,0x387fb371,0x3a2d3beb,
  0xbac7bb76,0x3a00ad33,0x36bb3bd4,0xbbeab79b,0xbc0026ad,0x3bf32c38,0xbbd6b109,0x3ba733eb,0x3153bbff,0xb70a3b9e,0x396bba9b,0xbade390c,
  0xb5d4b5bc,0xbbb03b2c,0x32013830,0x3bf6ba67,0x3bccbb52,0x2c06b92e,0xbb83385f,0xb8c73bab,0xb9c5b982,0xba41ba04,0xbab0ba7a,0xbb10bae1,
  0xb8a3b986,0xb52fb74e,0xa94db1e8,0x33d32e91,0xbb54bb4f,0x37bdb523,0x3a9e3bc8,0xb916308d,0x3840b5c8,0x394a3bf9,0xbb42b294,0xb0a6bb0a,
  0x251bbbff,0xaf273bfc,0x327cbbe6,0xb4ab3bc0,0x3be325e4,0xbb2fb4e7,0x39e33884,0xb81aba35,0x3b73bb78,0xb46fb715,0xbbdc3ad1,0x2e2d38cc,
  0x33283676,0x3bfcba19,0x3581bab3,0xba6b3493,0x363136dd,0x34cf3581,0x32c6341a,0x2fbd3153,0xbae1bb65,0xb970ba39,0xb715b889,0xb16cb4f3,
  0xb9a12a7a,0xb924bbfe,0x3a933042,0x37dd3bcc,0x308db9aa,0x3b453b07,0xb94632ad,0xb845bbfa,0xbb68b55e,0x3b1836bb,0xbabab805,0x3a4d38a3,
  0x3bc0b625,0xbbfe2ec3,0x3b9431cf,0xba89b742,0x9cb6b95d,0xbbf8396b,0xb1b63a5c,0x3bb5b840,0x38cc9648,0x3b81bbac,0xac38b85a,0xbbce3933,
  0xbb60bb3a,0xbba1bb83,0xbbd2bbbc,0xbbf1bbe3,0x3815361a,0x39df3907,0x3b2c3a97,0x3be23b9c,0xb9afbbfd,0x3a21294d,0x388e3bee,0xbaf7b328,
  0x3beb39a6,0xb6af37a6,0xba04bbd3,0x3ac42d00,0x360ebb89,0xb7643b42,0x3855baeb,0xb8ee3a85,0x33eb3b63,0x28e8bbf5,0xb5233bde,0x389ebb21,
  0x3c00b9f0,0x2d97b9e3,0xbbdf38db,0xb44b3ac7,0xba673c00,0x358d3487,0x3bfcbab6,0x330fba15,0x3b7a3bf1,0x394a3a93,0x33893764,0xb3d39cb6,
  0x3afb3be2,0x35eb3946,0xb4c328e8,0xbaa9b8cc,0x27763af7,0xbb2fbaba,0x3a76ad97,0x30a63b60,0xaf8b3ac4,0xb994bb94,0x3bf8358d,0xb8743815,
  0xbb4c38ee,0x3bfcb1b6,0xbad5b4cf,0x381a39af,0xbbb3389e,0x3b592c38,0xb76fb970,0xb24b3beb,0xb9d2344b,0xbb923bd2,0xb0f03924,0x3a6bb60e,
  0xb8f3330f,0xbc003b2c,0xb91f3b45,0x323233eb,0xb5b1afbd,0xba00b88e,0xbbc6bb18,0xbbc2bc00,0xb7d2b16c,0xbb6fba04,0xbba3bbfe,0xb86fba67,
  0xbbffb7dd,0x370ab855,0x38b73bf8,0xbbeab631,0xbbf2b845,0x39bcb523,0x2dc93b81,0xbaa5bae1,0xb68dba4d,0xac063bdf,0x382abba1,0xbade39a1,
  0xb457ba89,0xb6543bfc,0x3b16b9df,0xbbd8308d,0x397dbbb5,0xb52fb2c6,0xbbe73a21,0xb8c73b68,0x3a49bbce,0x2311b715,0xba2536af,0xbbd93bc0,
  0xb958b785,0xbb81ba9e,0xbbefbbf3,0xba89bb73,0xbbf7bbc2,0xb9b8bb42,0xaf59b70a,0x384a3328,0xbb8bba2d,0x39dfb27c,0x34263bb0,0xbbceb98b,
  0xb4b7bbea,0x3b6c39e3,0xbafe2c06,0x3185ba85,0xaadebba7,0xb6af3bdc,0x3a58ba41,0xbbe2366b,0x3a29bade,0xbc003581,0x3a45352f,0xb2f7bac7,
  0x3b37bbf6,0x28e8b865,0xbaee37bd,0xbac43c00,0x3b13b8c7,0x3b5cbbfe,0x3463b94a,0xb8993153,0xb9f4bb10,0xb58db87f,0x3029af27,0x389e35d4,
  0x2dfbb3d3,0x399936bb,0x3bf23b2f,0x3ac13bcc,0x3552b916,0x39703bd6,0xbbbab46f,0x330fb9c5,0x3ba530a6,0xb5f7396b,0xb7c8bbfc,0x3be138a3,
  0x3bfdb4ab,0xbb45b201,0x38e038fd,0xb16cbb54,0x391b381a,0xa17fbb83,0xb8f83b92,0x3bcfb840,0x36e82e2d,0x3bfebab0,0x37febb01,0xb845251b,
  0xb77a3a6b,0x3648294d,0x3bb2ba00,0x3a8cbbe3,0xb742b93c,0x2311b340,0x37a6340e,0x3aa93966,0x3b963a4d,0x3b7f3c00,0x380f3a21,0xb0be3219,
  0x3933b50b,0x35eb3be4,0xbbf5b8d6,0x3874b6c6,0x39413bb5,0xbbffb65f,0x38d1b764,0x33ba3bd7,0x3b9c2c9c,0xb994b83a,0x34873ae8,0x324bbbfe,
  0xb7213bf1,0x3b47b990,0xbbbf2d97,0x38c1387a,0x2d00372c,0x3b59b8a8,0x3a39bbed,0xb232b576,0xbbfb3af7,0xb9743b71,0x307434cf,0x3adbb86a,
  0x3b213a0d,0x3c003bcb,0x3b073bbd,0x386f39e7,0x351738ee,0xb599a452,0xbae5b924,0xbbe9bbda,0x3a153b98,0xbb6fb13b,0x2ec3ba60,0x3aa53b3f,
  0xba09344b,0xa884bb57,0x3a643b18,0xbbc3b263,0xb4f33bfb,0x39bcbacb,0xbbac380a,0x3bd8a9b1,0xbb2aafbd,0x36a439c0,0x3402bbf8,0xba6f3aa2,
  0xbbfa3b27,0xb6543a81,0x3907b05b,0x3bd9bb85,0x2c6ab7dd,0xb9da35df,0xbbec3ba1,0xb8203aac,0x3bf53b87,0x3b6c3bec,0x392e3a7e,0x32f73721,
  0xb9e7b785,0xbbfcbb5e,0xba81bbb0,0xb43eb894,0x379b3bfe,0xbc00b80f,0x374eb835,0x38993bfb,0xbb3fba2d,0x3b329fdb,0xb3403a41,0xb8eabbd0,
  0xb90c3b3d,0x3b5cb8d1,0xbbf93122,0x3ac13517,0x29b1bba7,0xb94f3b6a,0x3be4b7bd,0xbaf4b19e,0xbbab3962,0xb9993bbf,0x34e73359,0x3be1ba09,
  0x3b85bbf6,0x353ab99d,0xb83a2f27,0xbbf03abd,0x2e91356a,0xb5f7b074,0xba19b8ad,0xbbcfbb2a,0xb966bb10,0xaba7b63c,0x38a8346f,0x3bb73a90,
  0xbb0aaa16,0xa17fbae5,0x3b1e3ace,0xba8c2c6a,0x36c6b916,0x36ff3c00,0xbbcbb8fd,0x3a50b2de,0xba35b6d2,0x36483a64,0x2d33bbe5,0xb84a3b96,
  0x3bfeb4ab,0xb9fcb602,0x313b3b01,0x37e8bbe0,0x3493b9eb,0xb9b83402,0xbb9e3bc9,0xb1853941,0x35762e2d,0x3b90b9b3,0x3acbbbf3,0x2fefb850,
  0x3a543bcf,0x2884374e,0xb9f8b648,0xbbe9bbab,0x398b3bb7,0xb4db3340,0xbbdcb9fc,0xb911bb85,0xb4323a8c,0xb6a4bbf9,0x3b3539b8,0xbbc3ae91,
  0xb66b3a50,0xad65bbe4,0x38653b90,0xbb0db966,0xbbef384a,0x39da34e7,0x2b43bb6c,0xba6f3b0a,0xbc0037e8,0x3759383a,0x387fbbfc,0xbbf636c6,
  0xb7f33185,0xbb7f3a19,0xbb8e3c00,0xb8203a35,0xb5d42fef,0xba1d38a8,0xbbd63b32,0xbba93bfe,0xb8e5b2f7,0xbbffbb1e,0xb954bb5c,0x30beb493,
  0xb9c5b43e,0xbb9fbbcb,0xb201b94f,0x3a313576,0xbbb8b899,0x3b47ad33,0xb6f43999,0xb3babbf5,0xbb54b8ea,0x3bf9313b,0xbab0353a,0x3790b9e7,
  0xb010bac1,0xb9743b9e,0x3bfdb5f7,0xb8c1b79b,0x251bbaf4,0xbb1b3acb,0x3a9e2ba7,0x2e5fbb3f,0x3af1bbe1,0x3599b92e,0xb546a17f,0xbadb390c,
  0x3b73bbf0,0x3929ba81,0x327cb6ff,0xb49f29b1,0xb825baa9,0x353aaec3,0x3b7c3994,0x3af43bfa,0x360eb0be,0x3bf43a64,0x388e3b47,0xb7372c6a,
  0x38bcb874,0x2ba73bac,0xb979bb59,0x3bf03742,0x3c0033ba,0xbb043402,0x3855b974,0xacce3b96,0x3bc5b24b,0xb6ffb907,0xb6993c00,0x3bb7b933,
  0x363138c1,0x3902bbec,0xbbdf3599,0x34ff3941,0x30d73232,0x39fcb7a6,0x3bffbb6f,0x3a50bb9c,0xb9a13adb,0xb47b380f,0x32c62884,0x3937b721,
  0x3ad8386f,0x3b903bf5,0x35a539bc,0xb7e8ad00,0x3b683be9,0x2ef538d1,0xba93b6a4,0xbb24bbfb,0x3a733aa5,0xbbfcb487,0x39d6b654,0xafef3b21,
  0x1cb63bc3,0xb7b2bbbf,0x3aba39da,0xbbfab517,0xb3a23bd8,0x3b32ba39,0xbb4a2311,0x343e3a15,0xbb603a6f,0x3a3d3074,0x31b6bb7f,0xbb9a3a09,
  0xbbe83bd9,0xb94f3b07,0xa81f35eb,0x38eab4f3,0xb9af3820,0xbbae3ae5,0xbbd23bff,0xba113b2a,0x319e389e,0xb929b426,0xbc00bb45,0xb911bb37,
  0xbbffbac1,0xb805bafe,0x382a217f,0x3bfd3b13,0xbabd330f,0x34dbba58,0x36023bfe,0xbb0db9f4,0xb68dbbe1,0x3a5c3a45,0xbbe7b648,0x3b89adfb,
  0xba90b16c,0x2d653aee,0x39b3bb81,0xbbf63552,0x397dbbcf,0xbbbc3463,0x338939b8,0x39f0bba5,0x32deb845,0xb7593029,0xbb5e39df,0xbba93bfd,
  0x3b7aba8c,0x3beebbf2,0x3a76bb6c,0x36ddb91b,0xbbe0ba89,0xba1dbbba,0x1fdbb6af,0x3a3136e8,0xa776b84a,0x3aeb37c8,0x3ad53c00,0xaa7a377a,
  0xb850bbce,0x3b9f38e0,0xbb6a28e8,0x3790b958,0x3b4cb185,0xb8db38f8,0x30f0bb5c,0x355e3bf7,0x3894bbe2,0xbbf937fe,0x399d358d,0x2e5fbb8b,
  0x39d232f7,0x341abbb2,0xbbc63999,0x395d34b7,0x3bd0bac4,0x3b1bbbef,0x363cb970,0xb49faade,0xb5b13899,0x30422f59,0x38b7b5f7,0x3b3aba29,
  0x3219b3d3,0x3b0438b7,0x3b713bfc,0x34ff397d,0x36e83aa9,0xb8b2adc9,0xbbefbb59,0xb5bcba49,0x3bd730a6,0xb902382a,0xa452bb92,0x39373b7a,
  0xb9583874,0x3371bb16,0x34263c00,0xb982bafb,0x387a381a,0x347bbbe7,0xbb573a00,0x3b242776,0xbb8b324b,0x31093a25,0x3a58bb6f,0xbb4f2f8b,
  0xb86a3a6b,0x2ef53389,0x39c0b70a,0x3bfabb4c,0xaadeb232,0xb83034c3,0xbaee39bc,0xbbff3bb3,0x3bda3bc2,0x37b23a76,0xb5df2c06,0xbb9ab9d2,
  0xbb37b86f,0xba7abbf8,0x3029b654,0x3b7838f3,0x32633bea,0xba3dbad5,0x3c00352f,0xba1135b1,0xb9f4baa5,0x3bc8376f,0xbbba2311,0x39cdb7d2,
  0xbaa23ade,0x3baeb0f0,0xb65fb94a,0xb7373bff,0x3552bbd8,0xbbe6391f,0x38e035eb,0x3682bbf2,0xbaac38c7,0xbbf43bc6,0xb9903b2f,0xacce368d,
  0x3bfdbbd9,0x3ad1bba3,0x37feb994,0x26adb457,0x38a33b9a,0xb8dba452,0xbb83bbae,0x2a7ab86a,0x37423b78,0xbab6b426,0xb907bbe6,0x39aa2ade,
  0xb8403a11,0x341abb57,0x294d3bf4,0xb55ebbda,0xb93339cd,0x3889ba58,0xb7a63ad1,0x3625bb37,0xbbe33737,0x304239c0,0x3b42bb04,0xb95db263,
  0xbb9c3682,0xb2ad3aee,0x3bf5b8b2,0x1648b9f4,0xb3282cce,0xb80535df,0xb9e33902,0xbb3a3aa2,0xad0026ad,0xb1cf3029,0xb4873371,0xb61a3552,
  0xba85b4ff,0xba5cbc00,0x3581b47b,0x3bfd3aac,0xbb21b5bc,0xb85abbba,0x3a393109,0x39a63bfd,0xbac7b937,0x3bbc365f,0xbbfeaef5,0x3b89b219,
  0xba15b982,0x3a9738e0,0xbb07b830,0x3b6336e8,0x3153bb24,0xbbee3990,0x36bb37b2,0x39f0bbd7,0x34f3bb4f,0xbbd337fe,0xaec33a7a,0x3c00b958,
  0x3bccbbfa,0x3aebbb71,0x396bba3d,0x36ddb87a,0x3bfabbff,0x3bdebbef,0x3bacbbc8,0x3b65bb8b,0x3bc03911,0x38303b6a,0xb946ad65,0xbb4fbbd0,
  0x3a353bfd,0xb85f30f0,0xbb1ebbbc,0x35c8b5b1,0x38cc3b0d,0xba7ab99d,0x3b943759,0xbbffb19e,0xb4933b89,0x31e8bbc6,0xad333bee,0xa5e4bbff,
  0xb8153bf6,0x3bc8b63c,0xac38ba1d,0xbb783abd,0xbbf539f0,0x329438b7,0x3b9ebaeb,0xb676b68d,0xbbeb3ba9,0xbbe63c00,0xbb2c3b9f,0xb9cd3a90,
  0xb79b36dd,0xb884382a,0xb92e38db,0xb9c9397d,0x33eb3a31,0xbad1b602,0xba04bbf9,0x3682b2de,0xb90c2a7a,0xbab3bbe7,0x374eb41a,0x3b763b7a,
  0xba673790,0x38b2b9b3,0xb5233b1b,0x26adbbe0,0xbbabb55e,0x3bdd3389,0xbbf9b042,0x3bff2776,0xbae12e5f,0xb3713b5e,0x3bfcb929,0xb5bcb850,
  0xae91b95d,0xbbd43a76,0x34e73805,0x3b52bb4c,0x308db49f,0xb1091fdb,0xb71534db,0xb9823894,0x3b0abb3a,0x3a9bbad5,0x3a19ba5c,0x3986b9d2,
  0x2f8bb7e8,0x3bde3979,0x376f3b32,0xb9aab0d7,0x3bb83b24,0xb1223855,0xbbfdba3d,0xaa16b9a1,0x3bb3afef,0xbab63699,0x391fb94f,0xb6253ad8,
  0x30103bfa,0xb359bbdf,0x35463bae,0xb6d2bb68,0x38f3343e,0x3889bbff,0xbba3353a,0x96483a73,0xbaf13b9a,0x38ad32c6,0x39f8bbf4,0xb9eb9cb6,
  0xb7d238ea,0xb2ad35a5,0x2dc92ba7,0x361ab3a2,0xba543a11,0xbace3a93,0xbb353b04,0xbb873b60,0x3bf23af4,0x31cf39d6,0xbb16b6ff,0xb9a6bbe8,
  0xb4323737,0xbbe5baba,0x2b43b902,0x3bfe39af,0x34573bf0,0xb85abb4a,0x3a2539fc,0xbb63b825,0xbbef2cce,0x3bc9b1b6,0xbb8e347b,0x3b3db60e,
  0xba493bb7,0x3a97a81f,0x34c3bb90,0xbc0038bc,0xb7f3b4ff,0xba7e3bd2,0x39542ef5,0x3962bc00,0xbafb3a50,0xbbd33b7c,0xbbf83bfc,0xbb653bc5,
  0x38e5b937,0x3835b88e,0x36f4b7b2,0x356ab631,0xbb13bbe9,0x31e8b6f4,0x3bf239da,0x36763af1,0x3be83911,0x340e3ab0,0xbb7cb759,0xb72cbb73,
  0x2dfbbbc3,0x32943bfd,0xb7c8bb7f,0x39c93a54,0x38253b0d,0xb8d6ba9e,0x39793a1d,0xba0db98b,0x3ba5ba6f,0xb884b546,0xb8f83bff,0x3b76b432,
  0xb8bc3bf6,0x3ae8b27c,0x3699bb9f,0xbb98366b,0x391bb820,0x3ab3b9f8,0x3bb2bb47,0x3bffbbef,0xbbc53ba9,0xbbed3bdc,0xbbff3bf9,0xbbfb3c00,
  0x377ab0be,0x3bdd3b35,0x2f593974,0xbb52b7f3,0x30d73a31,0xbbbdb865,0xb5a5bb1b,0x3b2735d4,0x3bf733ba,0xbbd42b43,0x3afeb599,0xb98638e5,
  0xbad83790,0x3a60b87f,0xb9d63929,0x393cb9c5,0x34b738c1,0x3a9bbb8e,0xba45a884,0xb5c83bb8,0xba732e5f,0xb80a3bd6,0x3b4ab4db,0x350bbb54,
  0xba293adb,0xb85f3954,0xb46336a4,0x25e43010,0x33a2b49f,0x305bb201,0x281fad65,0xac9c251b,0x3f803f80,0x3f803f80,0x3f803f80,0x3f803f80,
  0x3f803f80,0x3f803f80,0x3f803f80,0x3f803f80,0x3f803f80,0x3f803f80,0x3f803f80,0x3f803f80,0x3f803f80,0x3f803f80,0x3f803f80,0x3f803f80,
  0x3f803f80,0x3f803f80,0x3f803f80,0x3f803f80,0x3f803f80,0x3f803f80,0x3f803f80,0x3f803f80,0x3f803f80,0x3f803f80,0x3f803f80,0x3f803f80,
  0x3f803f80,0x3f803f80,0x3f803f80,0x3f803f80,0x3f803f80,0x3f803f80,0x3f803f80,0x3f803f80,0x3f803f80,0x3f803f80,0x3f803f80,0x3f803f80,
  0x3f803f80,0x3f803f80,0x3f803f80,0x3f803f80,0x3f803f80,0x3f803f80,0x3f803f80,0x3f803f80,0x3f803f80,0x3f803f80,0x3f803f80,0x3f803f80,
  0x3f803f80,0x3f803f80,0x3f803f80,0x3f803f80,0x3f803f80,0x3f803f80,0x3f803f80,0x3f803f80,0x3f803f80,0x3f803f80,0x3f803f80,0x3f803f80,
  0x3f803f80,0x3f803f80,0x3f803f80,0x3f803f80,0x3f803f80,0x3f803f80,0x3f803f80,0x3f803f80,0x3f803f80,0x3f803f80,0x3f803f80,0x3f803f80,
  0x3f803f80,0x3f803f80,0x3f803f80,0x3f803f80,0x3f803f80,0x3f803f80,0x3f803f80,0x3f803f80,0x3f803f80,0x3f803f80,0x3f803f80,0x3f803f80,
  0x3f803f80,0x3f803f80,0x3f803f80,0x3f803f80,0x3f803f80,0x3f803f80,0x3f803f80,0x3f803f80,0x3f803f80,0x3f803f80,0x3f803f80,0x3f803f80,
  0x3f803f80,0x3f803f80,0x3f803f80,0x3f803f80,0x3f803f80,0x3f803f80,0x3f803f80,0x3f803f80,0x3f803f80,0x3f803f80,0x3f803f80,0x3f803f80,
  0x3f803f80,0x3f803f80,0x3f803f80,0x3f803f80,0x3f803f80,0x3f803f80,0x3f803f80,0x3f803f80,0x3f803f80,0x3f803f80,0x3f803f80,0x3f803f80,
  0x3f803f80,0x3f803f80,0x3f803f80,0x3f803f80,0x3f803f80,0x3f803f80,0x3f803f80,0x3f803f80,0x3f803f80,0x3f803f80,0x3f803f80,0x3f803f80,
  0x3f803f80,0x3f803f80,0x3f803f80,0x3f803f80,0x3f803f80,0x3f803f80,0x3f803f80,0x3f803f80,0x3f803f80,0x3f803f80,0x3f803f80,0x3f803f80,
  0x3f803f80,0x3f803f80,0x3f803f80,0x3f803f80,0x3f803f80,0x3f803f80,0x3f803f80,0x3f803f80,0x3f803f80,0x3f803f80,0x3f803f80,0x3f803f80,
  0x3f803f80,0x3f803f80,0x3f803f80,0x3f803f80,0x3f803f80,0x3f803f80,0x3f803f80,0x3f803f80,0x3f803f80,0x3f803f80,0x3f803f80,0x3f803f80,
  0x3f803f80,0x3f803f80,0x3f803f80,0x3f803f80,0x3f803f80,0x3f803f80,0x3f803f80,0x3f803f80,0x3f803f80,0x3f803f80,0x3f803f80,0x3f803f80,
  0x3f803f80,0x3f803f80,0x3f803f80,0x3f803f80,0x3f803f80,0x3f803f80,0x3f803f80,0x3f803f80,0x3f803f80,0x3f803f80,0x3f803f80,0x3f803f80,
  0x3f803f80,0x3f803f80,0x3f803f80,0x3f803f80,0x3f803f80,0x3f803f80,0x3f803f80,0x3f803f80,0x3f803f80,0x3f803f80,0x3f803f80,0x3f803f80,
  0x3f803f80,0x3f803f80,0x3f803f80,0x3f803f80,0x3f803f80,0x3f803f80,0x3f803f80,0x3f803f80,0x3f803f80,0x3f803f80,0x3f803f80,0x3f803f80,
  0x3f803f80,0x3f803f80,0x3f803f80,0x3f803f80,0x3f803f80,0x3f803f80,0x3f803f80,0x3f803f80,0x3f803f80,0x3f803f80,0x3f803f80,0x3f803f80,
  0x3f803f80,0x3f803f80,0x3f803f80,0x3f803f80,0x3f803f80,0x3f803f80,0x3f803f80,0x3f803f80,0x3f803f80,0x3f803f80,0x3f803f80,0x3f803f80,
  0x3f803f80,0x3f803f80,0x3f803f80,0x3f803f80,0x3f803f80,0x3f803f80,0x3f803f80,0x3f803f80,0x3f803f80,0x3f803f80,0x3f803f80,0x3f803f80,
  0x3f803f80,0x3f803f80,0x3f803f80,0x3f803f80,0x3f803f80,0x3f803f80,0x3f803f80,0x3f803f80,0x3f803f80,0x3f803f80,0x3f803f80,0x3f803f80,
  0x3f803f80,0x3f803f80,0x3f803f80,0x3f803f80,0x3f803f80,0x3f803f80,0x3f803f80,0x3f803f80,0x3f803f80,0x3f803f80,0x3f803f80,0x3f803f80,
  0x3f803f80,0x3f803f80,0x3f803f80,0x3f803f80,0x3f803f80,0x3f803f80,0x3f803f80,0x3f803f80,0x3f803f80,0x3f803f80,0x3f803f80,0x3f803f80,
  0x3f803f80,0x3f803f80,0x3f803f80,0x3f803f80,0x3f803f80,0x3f803f80,0x3f803f80,0x3f803f80,0x3f803f80,0x3f803f80,0x3f803f80,0x3f803f80,
  0x3f803f80,0x3f803f80,0x3f803f80,0x3f803f80,0x3f803f80,0x3f803f80,0x3f803f80,0x3f803f80,0x3f803f80,0x3f803f80,0x3f803f80,0x3f803f80,
  0x3f803f80,0x3f803f80,0x3f803f80,0x3f803f80,0x3f803f80,0x3f803f80,0x3f803f80,0x3f803f80,0x3f803f80,0x3f803f80,0x3f803f80,0x3f803f80,
  0x3f803f80,0x3f803f80,0x3f803f80,0x3f803f80,0x3f803f80,0x3f803f80,0x3f803f80,0x3f803f80,0x3f803f80,0x3f803f80,0x3f803f80,0x3f803f80,
  0x3f803f80,0x3f803f80,0x3f803f80,0x3f803f80,0x3f803f80,0x3f803f80,0x3f803f80,0x3f803f80,0x3f803f80,0x3f803f80,0x3f803f80,0x3f803f80,
  0x3f803f80,0x3f803f80,0x3f803f80,0x3f803f80,0x3f803f80,0x3f803f80,0x3f803f80,0x3f803f80,0x3f803f80,0x3f803f80,0x3f803f80,0x3f803f80,
  0x3f803f80,0x3f803f80,0x3f803f80,0x3f803f80,0x3f803f80,0x3f803f80,0x3f803f80,0x3f803f80,0x3f803f80,0x3f803f80,0x3f803f80,0x3f803f80,
  0x3f803f80,0x3f803f80,0x3f803f80,0x3f803f80,0x3f803f80,0x3f803f80,0x3f803f80,0x3f803f80,0x3f803f80,0x3f803f80,0x3f803f80,0x3f803f80,
  0x3f803f80,0x3f803f80,0x3f803f80,0x3f803f80,0x3f803f80,0x3f803f80,0x3f803f80,0x3f803f80,0x3f803f80,0x3f803f80,0x3f803f80,0x3f803f80,
  0x3f803f80,0x3f803f80,0x3f803f80,0x3f803f80,0x3f803f80,0x3f803f80,0x3f803f80,0x3f803f80,0x3f803f80,0x3f803f80,0x3f803f80,0x3f803f80,
  0x3f803f80,0x3f803f80,0x3f803f80,0x3f803f80,0x3f803f80,0x3f803f80,0x3f803f80,0x3f803f80,0x3f803f80,0x3f803f80,0x3f803f80,0x3f803f80,
  0x3f803f80,0x3f803f80,0x3f803f80,0x3f803f80,0x3f803f80,0x3f803f80,0x3f803f80,0x3f803f80,0x3f803f80,0x3f803f80,0x3f803f80,0x3f803f80,
  0x3f803f80,0x3f803f80,0x3f803f80,0x3f803f80,0x3f803f80,0x3f803f80,0x3f803f80,0x3f803f80,0x3f803f80,0x3f803f80,0x3f803f80,0x3f803f80,
  0x3f803f80,0x3f803f80,0x3f803f80,0x3f803f80,0x3f803f80,0x3f803f80,0x3f803f80,0x3f803f80,0x3f803f80,0x3f803f80,0x3f803f80,0x3f803f80,
  0x3f803f80,0x3f803f80,0x3f803f80,0x3f803f80,0x3f803f80,0x3f803f80,0x3f803f80,0x3f803f80,0x3f803f80,0x3f803f80,0x3f803f80,0x3f803f80,
  0x3f803f80,0x3f803f80,0x3f803f80,0x3f803f80,0x3f803f80,0x3f803f80,0x3f803f80,0x3f803f80,0x3f803f80,0x3f803f80,0x3f803f80,0x3f803f80,
  0x3f803f80,0x3f803f80,0x3f803f80,0x3f803f80,0x3f803f80,0x3f803f80,0x3f803f80,0x3f803f80,0x3f803f80,0x3f803f80,0x3f803f80,0x3f803f80,
  0x3f803f80,0x3f803f80,0x3f803f80,0x3f803f80,0x3f803f80,0x3f803f80,0x3f803f80,0x3f803f80,0x3f803f80,0x3f803f80,0x3f803f80,0x3f803f80,
  0x3f803f80,0x3f803f80,0x3f803f80,0x3f803f80,
};

__device__ __align__(128) float    g_part[16][8][2176];
__device__ __align__(128) float    g_kv[16][2176];
__device__ __align__(128) uint4    g_o[16 * 16 * 1024];
__device__ __align__(128) unsigned g_ocnt[16 * 32];
__device__ unsigned g_epoch[128];
#define GSTAMP(role, i) do {} while (0)
#define STAMP(role, i) do {} while (0)

constexpr int STAGE_BYTES = 57344;
constexpr int OFF_PK = 0, OFF_V = 114688, OFF_H = 4 * 16384, OFF_VP = 9 * 16384;
constexpr int OFF_XT = 172032, XT_STRIDE = 4112;
constexpr int OFF_BAR = 204928, OFF_EPOCH = OFF_BAR + 640, OFF_EX = OFF_BAR + 672, OFF_SCALE = OFF_BAR + 704;
constexpr int OFF_F2F = 205824, OFF_F2I = 207872, OFF_F4 = 209920, OFF_ONES = 214016, OFF_KVB = 214016;
constexpr int OFF_STG = 219136, STG_STRIDE = 4352, SMEM_TOTAL = 232192;
enum { B_FULL1 = 0, B_EMPTY1 = 3, B_H = 6, B_XRAW = 10, B_XT = 11, B_KV = 12, B_Y = 13, B_PKFREE = 14, B_AFREE = 15,
       B_STG = 18, B_ODONE = 24, B_XFREE = 25, B_FULL2 = 33, B_CONS2 = 49, B_S1FREE = 62, B_COUNT = 63 };
__host__ __device__ constexpr int bar_count(int i) {
  return i < B_EMPTY1 ? 1 : i < B_H ? 4 : i < B_XRAW ? 2 : i == B_XT ? 9 : i == B_KV ? 2 : i == B_PKFREE ? 4
       : (i >= B_AFREE && i < B_STG) ? 16 : i == B_ODONE ? 8 : (i >= B_XFREE && i < B_FULL2) ? 4
       : (i >= B_CONS2 && i <= B_CONS2 + 10) ? 4 : (i >= B_FULL2 && i < B_S1FREE) ? 2 : 1;
}
__host__ __device__ constexpr uint64_t bar_counts(int r) {
  uint64_t v = 0;
  for (int w = 0; w < 12; w++) v |= (uint64_t)(bar_count(12 * r + w) - 1) << (4 * w);
  return v;
}
constexpr uint64_t SLOT_A = 0x9645296452964594ull;
constexpr uint64_t SLOT_B = 0x7103871038710326ull;
constexpr int SPIN_LIMIT = 1 << 22;
#define HDELAY 1000
#define OC 1

__device__ __forceinline__ uint32_t smem_u32(const void* p) { return (uint32_t)__cvta_generic_to_shared(p); }
__device__ __forceinline__ void wg_fence() { asm volatile("wgmma.fence.sync.aligned;" ::: "memory"); }
__device__ __forceinline__ void wg_commit() { asm volatile("wgmma.commit_group.sync.aligned;" ::: "memory"); }
template <int N> __device__ __forceinline__ void wg_wait() { asm volatile("wgmma.wait_group.sync.aligned %0;" ::"n"(N) : "memory"); }
template <int N> __device__ __forceinline__ void keep(float (&d)[N]) {
#pragma unroll
  for (int i = 0; i < N; i++) asm volatile("" : "+f"(d[i])::"memory");
}
__device__ __forceinline__ uint64_t mkdesc(uint32_t addr, uint32_t lbo, uint32_t sbo, uint32_t swz) {
  uint32_t lo = ((addr & 0x3FFFF) >> 4) | ((lbo >> 4) << 16), hi = (sbo >> 4) | (swz << 30);
  return ((uint64_t)hi << 32) | lo;
}
__device__ __forceinline__ void mbar_init(uint32_t bar, int cnt) { asm volatile("mbarrier.init.shared::cta.b64 [%0], %1;" ::"r"(bar), "r"(cnt)); }
__device__ __forceinline__ void mbar_expect(uint32_t bar, int bytes) { asm volatile("mbarrier.arrive.expect_tx.shared::cta.b64 _, [%0], %1;" ::"r"(bar), "r"(bytes) : "memory"); }
__device__ __forceinline__ void mbar_arrive(uint32_t bar) { asm volatile("mbarrier.arrive.shared::cta.b64 _, [%0];" ::"r"(bar) : "memory"); }
__device__ __forceinline__ void mbar_arrive_cl(uint32_t bar, uint32_t cta) {
  asm volatile("{\n.reg .b32 r;\nmapa.shared::cluster.u32 r, %0, %1;\nmbarrier.arrive.shared::cluster.b64 _, [r];\n}\n" ::"r"(bar), "r"(cta) : "memory");
}
__device__ __forceinline__ void mbar_wait(uint32_t bar, uint32_t parity) {
  asm volatile("{\n.reg .pred p;\n.reg .u32 n;\nmov.u32 n, 0;\n"
               "W_%=:\nmbarrier.try_wait.parity.shared::cta.b64 p, [%0], %1;\n@p bra D_%=;\n"
               "add.u32 n, n, 1;\nsetp.lt.u32 p, n, %2;\n@p bra W_%=;\ntrap;\nD_%=:\n}\n" ::"r"(bar), "r"(parity), "n"(SPIN_LIMIT) : "memory");
}
__device__ __forceinline__ void fence_async() { asm volatile("fence.proxy.async.shared::cta;" ::: "memory"); }
__device__ __forceinline__ void bar_sync(int id) { asm volatile("bar.sync %0, 128;" ::"r"(id) : "memory"); }
__device__ __forceinline__ void tma2d(uint32_t dst, const CUtensorMap* m, int c0, int c1, uint32_t bar) {
  asm volatile("cp.async.bulk.tensor.2d.shared::cluster.global.mbarrier::complete_tx::bytes [%0], [%1, {%3, %4}], [%2];"
               ::"r"(dst), "l"(m), "r"(bar), "r"(c0), "r"(c1) : "memory");
}
__device__ __forceinline__ void tma2d_mc(uint32_t dst, const CUtensorMap* m, int c0, int c1, uint32_t bar) {
  asm volatile("cp.async.bulk.tensor.2d.shared::cluster.global.mbarrier::complete_tx::bytes.multicast::cluster [%0], [%1, {%3, %4}], [%2], %5;"
               ::"r"(dst), "l"(m), "r"(bar), "r"(c0), "r"(c1), "h"((uint16_t)3) : "memory");
}
__device__ __forceinline__ void tma3d(uint32_t dst, const CUtensorMap* m, int c0, int c1, int c2, uint32_t bar) {
  asm volatile("cp.async.bulk.tensor.3d.shared::cluster.global.mbarrier::complete_tx::bytes [%0], [%1, {%3, %4, %5}], [%2];"
               ::"r"(dst), "l"(m), "r"(bar), "r"(c0), "r"(c1), "r"(c2) : "memory");
}
__device__ __forceinline__ void bulk_ld(uint32_t dst, const void* src, int bytes, uint32_t bar) {
  asm volatile("cp.async.bulk.shared::cluster.global.mbarrier::complete_tx::bytes [%0], [%1], %2, [%3];" ::"r"(dst), "l"(src), "r"(bytes), "r"(bar) : "memory");
}
__device__ __forceinline__ void bulk_ld_mc(uint32_t dst, const void* src, int bytes, uint32_t bar) {
  asm volatile("cp.async.bulk.shared::cluster.global.mbarrier::complete_tx::bytes.multicast::cluster [%0], [%1], %2, [%3], %4;"
               ::"r"(dst), "l"(src), "r"(bytes), "r"(bar), "h"((uint16_t)3) : "memory");
}
__device__ __forceinline__ void tma2d_st(const CUtensorMap* m, uint32_t src, int c0, int c1) {
  asm volatile("cp.async.bulk.tensor.2d.global.shared::cta.bulk_group [%0, {%2, %3}], [%1];" ::"l"(m), "r"(src), "r"(c0), "r"(c1) : "memory");
}
__device__ __forceinline__ void pf_l2(const void* p, int bytes) { asm volatile("cp.async.bulk.prefetch.L2.global [%0], %1;" ::"l"(p), "r"(bytes) : "memory"); }
__device__ __forceinline__ void pf_t2d(const CUtensorMap* m, int c0, int c1) {
  asm volatile("cp.async.bulk.prefetch.tensor.2d.L2.global [%0, {%1, %2}];" ::"l"(m), "r"(c0), "r"(c1) : "memory");
}
__device__ __forceinline__ void pf_t3d(const CUtensorMap* m, int c0, int c1, int c2) {
  asm volatile("cp.async.bulk.prefetch.tensor.3d.L2.global [%0, {%1, %2, %3}];" ::"l"(m), "r"(c0), "r"(c1), "r"(c2) : "memory");
}
__device__ __forceinline__ void ldsm4(uint32_t (&r)[4], uint32_t a) {
  asm volatile("ldmatrix.sync.aligned.m8n8.x4.shared.b16 {%0,%1,%2,%3}, [%4];" : "=r"(r[0]), "=r"(r[1]), "=r"(r[2]), "=r"(r[3]) : "r"(a) : "memory");
}
__device__ __forceinline__ void ldsm4t(uint32_t (&r)[4], uint32_t a) {
  asm volatile("ldmatrix.sync.aligned.m8n8.x4.trans.shared.b16 {%0,%1,%2,%3}, [%4];" : "=r"(r[0]), "=r"(r[1]), "=r"(r[2]), "=r"(r[3]) : "r"(a) : "memory");
}
__device__ __forceinline__ void stsm4(uint32_t a, uint32_t r0, uint32_t r1, uint32_t r2, uint32_t r3) {
  asm volatile("stmatrix.sync.aligned.m8n8.x4.shared.b16 [%0], {%1,%2,%3,%4};" ::"r"(a), "r"(r0), "r"(r1), "r"(r2), "r"(r3) : "memory");
}
__device__ __forceinline__ uint32_t pk2(float lo, float hi) { uint32_t r; asm("cvt.rn.bf16x2.f32 %0, %1, %2;" : "=r"(r) : "f"(hi), "f"(lo)); return r; }
__device__ __forceinline__ uint32_t hmul(uint32_t a, uint32_t b) { uint32_t r; asm("mul.rn.bf16x2 %0, %1, %2;" : "=r"(r) : "r"(a), "r"(b)); return r; }
__device__ __forceinline__ uint32_t hadd(uint32_t a, uint32_t b) { uint32_t r; asm("add.rn.bf16x2 %0, %1, %2;" : "=r"(r) : "r"(a), "r"(b)); return r; }
__device__ __forceinline__ uint32_t hmax(uint32_t a, uint32_t b) { uint32_t r; asm("max.bf16x2 %0, %1, %2;" : "=r"(r) : "r"(a), "r"(b)); return r; }
__device__ __forceinline__ uint32_t hmin(uint32_t a, uint32_t b) { uint32_t r; asm("min.bf16x2 %0, %1, %2;" : "=r"(r) : "r"(a), "r"(b)); return r; }
__device__ __forceinline__ float ex2(float x) { float r; asm("ex2.approx.ftz.f32 %0, %1;" : "=f"(r) : "f"(x)); return r; }
__device__ __forceinline__ float rcp_fast(float x) { float r; asm("rcp.approx.ftz.f32 %0, %1;" : "=f"(r) : "f"(x)); return r; }
__device__ __forceinline__ uint32_t phi2(float lo, float hi) {
  uint32_t t = pk2(lo, hi);
  uint32_t e = pk2(ex2(lo * 1.4426950408889634f), ex2(hi * 1.4426950408889634f));
  return hadd(hmax(t, 0x35863586u), hmin(e, 0x3F803F80u));
}
__device__ __forceinline__ void poll_ge(const unsigned* p, unsigned target) {
#pragma unroll 1
  for (int n = 0; n < SPIN_LIMIT; n++) {
    unsigned v;
    asm volatile("ld.acquire.gpu.global.u32 %0, [%1];" : "=r"(v) : "l"(p) : "memory");
    if ((int)(v - target) >= 0) return;
  }
  __trap();
}

__device__ __forceinline__ uint32_t mapa(uint32_t a, uint32_t cta) { uint32_t r; asm("mapa.shared::cluster.u32 %0, %1, %2;" : "=r"(r) : "r"(a), "r"(cta)); return r; }
__device__ __forceinline__ void st_async(uint32_t a, uint32_t v, uint32_t bar) {
  asm volatile("st.async.weak.shared::cluster.mbarrier::complete_tx::bytes.b32 [%0], %1, [%2];" ::"r"(a), "r"(v), "r"(bar) : "memory");
}
__device__ __forceinline__ void st_async4(uint32_t a, uint32_t x, uint32_t y, uint32_t z, uint32_t w, uint32_t bar) {
  asm volatile("st.async.weak.shared::cluster.mbarrier::complete_tx::bytes.v4.b32 [%0], {%1,%2,%3,%4}, [%5];" ::"r"(a), "r"(x), "r"(y), "r"(z), "r"(w), "r"(bar) : "memory");
}
__device__ __forceinline__ void tma3d_st(const CUtensorMap* m, uint32_t src, int c0, int c1, int c2) {
  asm volatile("cp.async.bulk.tensor.3d.global.shared::cta.bulk_group [%0, {%2, %3, %4}], [%1];" ::"l"(m), "r"(src), "r"(c0), "r"(c1), "r"(c2) : "memory");
}
__device__ __forceinline__ uint4 ld_rlx4(const void* p) {
  uint4 v; asm volatile("ld.relaxed.gpu.global.v4.u32 {%0,%1,%2,%3}, [%4];" : "=r"(v.x), "=r"(v.y), "=r"(v.z), "=r"(v.w) : "l"(p) : "memory"); return v;
}
__device__ __forceinline__ uint32_t tagged(float v, uint32_t tag) { return (__float_as_uint(v) & ~1u) | tag; }
__device__ __forceinline__ void st_tag4(void* p, float a, float b, float c, float d, uint32_t tag) {
  asm volatile("st.relaxed.gpu.global.v4.u32 [%0], {%1,%2,%3,%4};" ::"l"(p), "r"(tagged(a, tag)), "r"(tagged(b, tag)), "r"(tagged(c, tag)), "r"(tagged(d, tag)) : "memory");
}
__device__ __forceinline__ uint32_t stale(uint4 v, uint32_t tag) { return (v.x ^ tag) | (v.y ^ tag) | (v.z ^ tag) | (v.w ^ tag); }

struct ConvC { uint32_t a1[2][4], wa[2], wb[2], sg; };
__device__ __forceinline__ uint64_t dsc(uint32_t lo, uint32_t hi) { return ((uint64_t)hi << 32) | lo; }
__device__ __forceinline__ uint32_t hfma(uint32_t a, uint32_t b, uint32_t c) { uint32_t r; asm("fma.rn.f16x2 %0, %1, %2, %3;" : "=r"(r) : "r"(a), "r"(b), "r"(c)); return r; }
__device__ __forceinline__ uint32_t hfnma(uint32_t a, uint32_t b, uint32_t c) { uint32_t r; asm("{.reg .b32 n; neg.f16x2 n, %1; fma.rn.f16x2 %0, n, %2, %3;}" : "=r"(r) : "r"(a), "r"(b), "r"(c)); return r; }
__device__ __forceinline__ uint32_t hmul16(uint32_t a, uint32_t b) { uint32_t r; asm("mul.rn.f16x2 %0, %1, %2;" : "=r"(r) : "r"(a), "r"(b)); return r; }
template <int N> __device__ __forceinline__ void keepu(uint32_t (&d)[N]) {
#pragma unroll
  for (int i = 0; i < N; i++) asm volatile("" : "+r"(d[i])::"memory");
}
__device__ __forceinline__ void conv_m1(const ConvC& K, uint32_t (&u)[16], uint32_t l) {
  wg_fence();
#pragma unroll
  for (int s = 0; s < 2; s++) wgmma_hrs_n64<1>(u, K.a1[s][0], K.a1[s][1], K.a1[s][2], K.a1[s][3], dsc(l + s * 16, 32), s);
  wg_commit();
}
__device__ __forceinline__ void conv_s2(const ConvC& K, uint32_t (&u)[16], uint32_t (&Z)[2][8], uint32_t dfl) {
  uint32_t fr[8], fi[8];
#pragma unroll
  for (int c = 0; c < 8; c++) {
    const uint32_t r = hfma(K.wa[c & 1], u[2 * c + 1], u[2 * c]);
    fi[c] = hfma(K.wb[c & 1], r, u[2 * c + 1]);
    fr[c] = hfma(K.wa[c & 1], fi[c], r);
  }
  wg_fence();
#pragma unroll
  for (int p = 0; p < 2; p++) {
    wgmma_hrs_n32<0>(Z[p], fr[4 * p], fr[4 * p + 2], fr[4 * p + 1], fr[4 * p + 3], dsc(dfl, 32), 0);
    wgmma_hrs_n32<0>(Z[p], fi[4 * p], fi[4 * p + 2], fi[4 * p + 1], fi[4 * p + 3], dsc(dfl + 16, 32), 1);
  }
  wg_commit();
}
__device__ __forceinline__ void conv_win(const ConvC& K, uint32_t (&X)[2][8]) {
#pragma unroll
  for (int b = 3; b >= 1; b--)
#pragma unroll
    for (int c = 0; c < 2; c++) {
      uint32_t& xr = X[b >> 1][2 * c + (b & 1)]; uint32_t& xi = X[b >> 1][4 + 2 * c + (b & 1)];
      xr = hfnma(K.sg, X[(b - 1) >> 1][4 + 2 * c + ((b - 1) & 1)], xr);
      xi = hfma(K.sg, X[(b - 1) >> 1][2 * c + ((b - 1) & 1)], xi);
    }
}
template <int p>
__device__ __forceinline__ void conv_pw(uint32_t (&X)[2][8], uint32_t (&H)[2][8], uint32_t (&V)[8], uint32_t dil) {
  uint32_t pr[2][2], pi[2][2];
#pragma unroll
  for (int jj = 0; jj < 2; jj++)
#pragma unroll
    for (int c = 0; c < 2; c++) {
      const int j = 2 * p + jj;
      uint32_t sr = 0, si = 0;
#pragma unroll
      for (int a = 0; a <= j; a++) {
        const int b = j - a;
        const uint32_t hr = H[a >> 1][2 * c + (a & 1)], hi = H[a >> 1][4 + 2 * c + (a & 1)];
        const uint32_t xr = X[b >> 1][2 * c + (b & 1)], xi = X[b >> 1][4 + 2 * c + (b & 1)];
        sr = a == 0 ? hmul16(hr, xr) : hfma(hr, xr, sr);
        si = a == 0 ? hmul16(hr, xi) : hfma(hr, xi, si);
        sr = hfnma(hi, xi, sr);
        si = hfma(hi, xr, si);
      }
      pr[jj][c] = sr; pi[jj][c] = si;
    }
  wg_fence();
  wgmma_hrs_n32<0>(V, pr[0][0], pr[1][0], pr[0][1], pr[1][1], dsc(dil, 32), 0);
  wgmma_hrs_n32<0>(V, pi[0][0], pi[1][0], pi[0][1], pi[1][1], dsc(dil + 16, 32), 1);
  wg_commit();
}
template <int p>
__device__ __forceinline__ void conv_it(const ConvC& K, uint32_t (&V)[8], uint32_t vst) {
#pragma unroll
  for (int jj = 0; jj < 2; jj++) {
    uint32_t wr[2], wi[2];
#pragma unroll
    for (int c = 0; c < 2; c++) {
      const uint32_t r = hfnma(K.wa[c], V[4 + 2 * c + jj], V[2 * c + jj]);
      wi[c] = hfnma(K.wb[c], r, V[4 + 2 * c + jj]);
      wr[c] = hfnma(K.wa[c], wi[c], r);
    }
    stsm4(vst + (2 * p + jj) * 2048, wr[0], wr[1], wi[0], wi[1]);
  }
}
__device__ __forceinline__ void conv_m4(uint32_t (&y)[8], uint32_t (&a)[4][4], uint32_t d4l) {
  wg_fence();
#pragma unroll
  for (int s = 0; s < 4; s++) wgmma_hrs_n32<0>(y, a[s][0], a[s][1], a[s][2], a[s][3], dsc(d4l + s * 16, 64), s);
  wg_commit();
}

struct Params {
  CUtensorMap tmX, tmW, tmWo, tmK, tmV, tmQ, tmOA, tmOB;
  const __nv_bfloat16 *shift_k, *h, *D;
};

__global__ void __cluster_dims__(2, 1, 1) __launch_bounds__(384, 1) fused_kernel(const __grid_constant__ Params P) {
  extern __shared__ __align__(1024) uint8_t smem[];
  const uint32_t sb = smem_u32(smem);
  const uint32_t bars = sb + OFF_BAR;
  const int tid = threadIdx.x, lane = tid & 31;
  const int warp = __shfl_sync(~0u, tid >> 5, 0);
  const int rank = blockIdx.x & 1, cl = blockIdx.x >> 1;
  const int mb = cl >> 3, hq = cl & 7;
  const int hp = 2 * hq + rank;
  const int rb = 2 * mb + (hq >> 2), cb = hq & 3;
#define BAR(i) (bars + 8 * (i))

  if (tid == 0) { STAMP(0, 0); GSTAMP(0, 30); }
  if (lane == 0) {
#pragma unroll
    for (int r = 0; r < 6; r++)
      if (r < 5 || warp < B_COUNT - 60) mbar_init(BAR(12 * r + warp), ((uint32_t)(bar_counts(r) >> (4 * warp)) & 15) + 1);
    asm volatile("fence.mbarrier_init.release.cluster;" ::: "memory");
  }
  asm volatile("barrier.cluster.arrive.relaxed.aligned;\nbarrier.cluster.wait.aligned;" ::: "memory");

  if (warp < 8) {
    asm volatile("setmaxnreg.inc.sync.aligned.u32 224;");
    const int wg = warp >> 2, w = warp & 3, g = lane >> 2, q = lane & 3, t = tid & 127;
    const bool elect = (t == 0);
    const uint32_t s16 = (sb & 0x3FFFF) >> 4;
    constexpr uint32_t SW128 = 64 | (1u << 30);
    uint32_t pq[2][16];
    ConvC K;
    {
      float acc[2][96];
      int st = 0, ph = 0;
#pragma unroll 1
      for (int kb = 0; kb < 16; kb++) {
        mbar_wait(BAR(B_FULL1 + st), ph);
        if (kb == 0 && elect) { STAMP(wg, 1); GSTAMP(wg, 26); }
        if (kb == 8 && elect) { STAMP(wg, 16); GSTAMP(wg, 25); }
        const uint32_t da = s16 + st * (STAGE_BYTES >> 4) + wg * 1024 + (1 << 16);
        const uint32_t db = s16 + st * (STAGE_BYTES >> 4) + 2048 + (512 << 16);
        wg_fence();
#pragma unroll
        for (int ks = 0; ks < 4; ks++) {
          wgmma_ss_n192<0, 1>(acc[0], dsc(da + ks * 2, SW128), dsc(db + ks * 128, SW128), (kb | ks) != 0);
          wgmma_ss_n192<0, 1>(acc[1], dsc(da + 512 + ks * 2, SW128), dsc(db + ks * 128, SW128), (kb | ks) != 0);
        }
        wg_commit();
        wg_wait<1>();
        if (kb > 0 && t < 2) mbar_arrive_cl(BAR(B_EMPTY1 + (st == 0 ? 2 : st - 1)), t);
        if (++st == 3) { st = 0; ph ^= 1; }
      }
      wg_wait<0>();
      keep(acc[0]); keep(acc[1]);
      if (t < 2) mbar_arrive_cl(BAR(B_EMPTY1 + 0), t);
      if (elect) { STAMP(wg, 2); GSTAMP(wg, 27); }
      const uint32_t lrow = sb + wg * 16384 + (16 * w + 8 * ((lane >> 3) & 1) + (lane & 7)) * 128 + (((lane >> 4) ^ (lane & 7)) << 4);
#pragma unroll
      for (int mt = 0; mt < 2; mt++)
#pragma unroll
        for (int cp = 0; cp < 4; cp++) {
          const float* a = &acc[mt][32 + 8 * cp];
          const float* b = &acc[mt][64 + 8 * cp];
          const uint32_t o = (lrow ^ (cp * 32)) + mt * 8192;
          stsm4(o + OFF_PK, phi2(a[0], a[1]), phi2(a[2], a[3]), phi2(a[4], a[5]), phi2(a[6], a[7]));
          stsm4(o + OFF_V, pk2(b[0], b[1]), pk2(b[2], b[3]), pk2(b[4], b[5]), pk2(b[6], b[7]));
        }
      fence_async();
      mbar_wait(BAR(B_XT), 0);
      {
        const uint4* ct = (const uint4*)c_thr + t;
#pragma unroll
        for (int s = 0; s < 2; s++) { uint4 u = __ldg(ct + s * 128); K.a1[s][0] = u.x; K.a1[s][1] = u.y; K.a1[s][2] = u.z; K.a1[s][3] = u.w; }
        uint4 u = __ldg(ct + 2 * 128);
        K.wa[0] = u.x; K.wa[1] = u.y; K.wb[0] = u.z; K.wb[1] = u.w;
        K.sg = (lane & 4) ? 0xBC00BC00u : 0x3C003C00u;
      }
      if (wg == 0) {
        asm volatile("bar.sync 3, 256;" ::: "memory");
        if (elect) STAMP(wg, 3);
        float kva[36];
        wg_fence();
#pragma unroll
        for (int ks = 0; ks < 16; ks++)
          wgmma_ss_n72<1, 1>(kva, dsc(s16 + (OFF_PK >> 4) + ks * 128 + (1 << 16), SW128),
                             dsc(s16 + (OFF_V >> 4) + ks * 128 + (((OFF_ONES - OFF_V - ks * 2048) >> 4) << 16), SW128), ks != 0);
        wg_commit();
        const uint32_t tag = ~*(volatile unsigned*)(smem + OFF_EPOCH) & 1;
        float* dst = &g_part[hp][mb][0];
        wg_wait<0>();
        keep(kva);
#pragma unroll
        for (int c = 0; c < 4; c++)
          st_tag4(dst + (c * 128 + t) * 4, w < 2 ? kva[4 * c] : kva[16 + 4 * c], w < 2 ? kva[4 * c + 1] : kva[17 + 4 * c],
                  w < 2 ? kva[4 * c + 2] : kva[18 + 4 * c], w < 2 ? kva[4 * c + 3] : kva[19 + 4 * c], tag);
        if (q < 2) asm volatile("st.relaxed.gpu.global.u32 [%0], %1;" ::"l"(dst + 2048 + 16 * w + g + 8 * q), "r"(tagged(q ? kva[34] : kva[32], tag)) : "memory");
        if (lane == 0) mbar_arrive(BAR(B_PKFREE));
      } else {
        asm volatile("bar.arrive 3, 256;" ::: "memory");
      }
      if (elect) STAMP(wg, 4);
#pragma unroll
      for (int mt = 0; mt < 2; mt++)
#pragma unroll
        for (int i = 0; i < 16; i++) pq[mt][i] = phi2(acc[mt][2 * i], acc[mt][2 * i + 1]);
      keepu(pq[0]); keepu(pq[1]);
    }
    mbar_wait(BAR(B_EMPTY1 + 2), 0);
    if (elect) STAMP(wg, 5);
    {
      const uint32_t dfl = s16 + (OFF_F2F >> 4) + (8 << 16), dil = s16 + (OFF_F2I >> 4) + (8 << 16), d4l = s16 + (OFF_F4 >> 4) + (8 << 16);
      const uint32_t xl = s16 + (OFF_XT >> 4) + 4 * wg * (XT_STRIDE >> 4) + (8 << 16);
      const uint32_t hl = s16 + (OFF_H >> 4) + wg * 512 + (8 << 16);
      uint32_t vst = sb + wg * 8192 + w * 512 + lane * 16, vld = sb + wg * 8192 + w * 2048 + lane * 16;
      uint32_t ya = mapa(sb + OFF_XT + 4 * wg * XT_STRIDE + (2 * rank + (w & 1)) * 1024 + lane * 16, w >> 1);
      const uint32_t ybar = mapa(BAR(B_Y), w >> 1);
      asm volatile("" : "+r"(vst), "+r"(vld), "+r"(ya));
      uint32_t ux[16], uh[16], X[4][2][8], H[4][2][8], V0[8], V1[8], y[8], a[4][4];
#define YOUT(i) do { mbar_wait(BAR(B_XFREE + 4 * wg + (i)), 0); \
        st_async4(ya + (i) * XT_STRIDE, y[0], y[2], y[4], y[6], ybar); \
        st_async4(ya + (i) * XT_STRIDE + 512, y[1], y[3], y[5], y[7], ybar); } while (0)
      conv_m1(K, ux, xl);
      mbar_wait(BAR(B_H + 0), 0);
      conv_m1(K, uh, hl);
      wg_wait<1>(); keepu(ux);
      if (lane == 0) mbar_arrive_cl(BAR(B_XFREE + 4 * wg), rank ^ 1);
      conv_s2(K, ux, X[0], dfl);
      wg_wait<1>(); keepu(uh);
      conv_s2(K, uh, H[0], dfl);
#pragma unroll
      for (int i = 0; i < 4; i++) {
        const bool nx = i < 3;
        const int n = nx ? i + 1 : i;
        const uint32_t vo = (i & 1) ? OFF_H + (i >> 1) * 16384 : OFF_VP;
        float oa[4][20];
        if (i == OC) {
          if (elect) STAMP(wg, 8);
          mbar_wait(BAR(B_KV), 0);
          if (elect) STAMP(wg, 9);
          wg_wait<0>();
          wg_fence();
#pragma unroll
          for (int m = 0; m < 8; m++) {
            const uint32_t* p = &pq[m >> 2][4 * (m & 3)];
            wgmma_rs_n40<1>(oa[m >> 1], p[0], p[1], p[2], p[3], dsc(s16 + (OFF_KVB >> 4) + ((m >> 1) & 1) * 160 + (m & 1) * 16 + (8 << 16), 32), m & 1);
          }
          wg_commit();
        }
        if (nx) {
          mbar_wait(BAR(B_H + n), 0);
          conv_m1(K, ux, xl + n * (XT_STRIDE >> 4));
          conv_m1(K, uh, hl + (n >> 1) * 1024 + (n & 1) * 256);
        }
        if (i == OC) { if (nx) wg_wait<2>(); else wg_wait<0>(); }
        else if (nx) { if (i > 0) wg_wait<3>(); else wg_wait<2>(); }
        else wg_wait<1>();
        if (i == OC) {
          uint4* ot = g_o + ((2 * mb + wg) * 16 + hp) * 1024 + (16 * w + g) * 8;
#pragma unroll
          for (int m = 0; m < 4; m++) {
            float (&o)[20] = oa[m];
            keep(o);
            const uint32_t den = hadd(pk2(o[16], o[18]), 0x35863586u);
#pragma unroll
            for (int r = 0; r < 2; r++) {
              const float ri = rcp_fast(__uint_as_float(r ? (den & 0xFFFF0000u) : (den << 16)));
              uint4 u;
              u.x = pk2(o[2 * r] * ri, o[2 * r + 1] * ri);
              u.y = pk2(o[4 + 2 * r] * ri, o[5 + 2 * r] * ri);
              u.z = pk2(o[8 + 2 * r] * ri, o[9 + 2 * r] * ri);
              u.w = pk2(o[12 + 2 * r] * ri, o[13 + 2 * r] * ri);
              __stcg(ot + (64 * (m >> 1) + 8 * r) * 8 + ((4 * (m & 1) + q) ^ g), u);
            }
          }
          __syncwarp();
          if (lane == 0) mbar_arrive(BAR(B_ODONE));
          if (elect) STAMP(wg, 10);
        }
        keepu(X[i][0]); keepu(X[i][1]); keepu(H[i][0]); keepu(H[i][1]);
        conv_win(K, X[i]);
        conv_pw<0>(X[i], H[i], V0, dil);
        conv_pw<1>(X[i], H[i], V1, dil);
        wg_wait<2>();
        if (i > 0) { keepu(y); YOUT(i - 1); }
        if (nx) {
          keepu(ux); keepu(uh);
          if (lane == 0) mbar_arrive_cl(BAR(B_XFREE + 4 * wg + n), rank ^ 1);
          conv_s2(K, ux, X[n], dfl);
          wg_wait<1>();
        } else wg_wait<0>();
        keepu(V0); keepu(V1);
        conv_it<0>(K, V0, vst + vo);
        conv_it<1>(K, V1, vst + vo);
        bar_sync(1 + wg);
#pragma unroll
        for (int s = 0; s < 4; s++) ldsm4t(a[s], vld + vo + s * 512);
        if (nx) conv_s2(K, uh, H[n], dfl);
        conv_m4(y, a, d4l);
        if (i > 0 && lane < 2) mbar_arrive_cl(BAR(B_AFREE + i - 1), lane);
        if (elect) STAMP(wg, i < 2 ? 6 + i : 9 + i);
      }
      wg_wait<0>(); keepu(y);
      YOUT(3);
    }
    {
      float acc[64];
#pragma unroll 1
      for (int kb = 0; kb < 16; kb++) {
        mbar_wait(BAR(B_FULL2 + kb), 0);
        if (kb == 0 && elect) { STAMP(wg, 13); GSTAMP(wg, 28); }
        const uint32_t da = s16 + ((uint32_t)(SLOT_A >> (4 * kb)) & 15) * 1024 + wg * 512 + (1 << 16);
        const uint32_t db = s16 + ((uint32_t)(SLOT_B >> (4 * kb)) & 15) * 1024 + (512 << 16);
        wg_fence();
#pragma unroll
        for (int ks = 0; ks < 4; ks++) wgmma_ss_n128<0, 1>(acc, dsc(da + ks * 2, SW128), dsc(db + ks * 128, SW128), (kb | ks) != 0);
        wg_commit();
        wg_wait<1>();
        if (kb > 0 && kb < 14 && t < 2 && (kb <= 11 || t == rank)) mbar_arrive_cl(BAR(B_CONS2 + kb - 1), t);
      }
      wg_wait<0>();
      keep(acc);
      if (elect) { STAMP(wg, 14); GSTAMP(wg, 29); }
      mbar_wait(BAR(B_CONS2 + 12), 0);
      const uint32_t stg = sb + (wg ? 5 : 3) * 16384;
      const uint32_t lrow = stg + (16 * w + 8 * ((lane >> 3) & 1) + (lane & 7)) * 128 + (((lane >> 4) ^ (lane & 7)) << 4);
#pragma unroll
      for (int cp = 0; cp < 8; cp++) {
        const float* a = &acc[8 * cp];
        stsm4((lrow ^ ((cp & 3) * 32)) + (cp >> 2) * 8192, pk2(a[0], a[1]), pk2(a[2], a[3]), pk2(a[4], a[5]), pk2(a[6], a[7]));
      }
      fence_async();
      bar_sync(1 + wg);
      if (elect) {
        const int col = 1024 + 256 * cb + 128 * rank, row = 128 * rb + 64 * wg;
        tma2d_st(&P.tmOB, stg, col, row);
        tma2d_st(&P.tmOB, stg + 8192, col + 64, row);
        asm volatile("cp.async.bulk.commit_group;\ncp.async.bulk.wait_group.read 0;" ::: "memory");
        STAMP(wg, 15); GSTAMP(wg, 31);
      }
    }
  } else {
    asm volatile("setmaxnreg.dec.sync.aligned.u32 56;");
    if (warp == 8) {
      if (lane == 0) {
        int st = 0, ph = 1;
#pragma unroll 1
        for (int kb = 0; kb < 16; kb++) {
          if (kb >= 3) mbar_wait(BAR(B_EMPTY1 + st), ph);
          const uint32_t sa = sb + st * STAGE_BYTES;
          mbar_expect(BAR(B_FULL1 + st), STAGE_BYTES);
          tma2d_mc(sa + rank * 16384, &P.tmX, kb * 64, mb * 256 + rank * 128, BAR(B_FULL1 + st));
          tma3d(sa + 32768, &P.tmW, hp * 64, kb * 64, 0, BAR(B_FULL1 + st));
          if (++st == 3) { st = 0; ph ^= 1; }
        }
        STAMP(2, 1);
        const unsigned epoch = g_epoch[blockIdx.x];
#pragma unroll 1
        for (int s = 0; s < 32; s++) {
          const bool isB = s < 7 || (s >= 14 && (s & 1));
          const int kb = s < 7 ? s : s < 14 ? s - 7 : s >> 1;
          if (s == 0) { mbar_wait(BAR(B_EMPTY1 + 1), 0); mbar_arrive(BAR(B_S1FREE)); }
          if (s == 1) mbar_wait(BAR(B_EMPTY1 + 0), 1);
          if (s == 7) {
            STAMP(2, 2);
            poll_ge(&g_ocnt[rb * 32], 16 * (epoch + 1));
            asm volatile("fence.proxy.async.global;" ::: "memory");
            STAMP(2, 3);
          }
          if (s >= 3) mbar_wait(BAR(s < 7 ? B_PKFREE : s < 10 ? B_AFREE + s - 7 : B_CONS2 + (s >> 1) - 5), 0);
          const uint32_t dst = sb + ((uint32_t)((isB ? SLOT_B : SLOT_A) >> (4 * kb)) & 15) * 16384;
          mbar_expect(BAR(B_FULL2 + kb), 16384);
          if (isB) tma3d(dst, &P.tmWo, 0, kb * 64, 4 * cb + 2 * rank, BAR(B_FULL2 + kb));
          else bulk_ld_mc(dst + rank * 8192, g_o + (rb * 16 + kb) * 1024 + rank * 512, 8192, BAR(B_FULL2 + kb));
          if (s == 9) STAMP(2, 4);
        }
        g_epoch[blockIdx.x] = epoch + 1;
        STAMP(2, 5);
      }
    } else {
      const int hw = warp - 9, g = lane >> 2, q = lane & 3;
      const unsigned epoch = g_epoch[blockIdx.x];
      const uint32_t tag = ~epoch & 1;
      const uint32_t stg = sb + OFF_STG + hw * STG_STRIDE, sbar = BAR(B_STG + 2 * hw);
      int ph = 0;
      {
        uint32_t tap[2][4];
#pragma unroll
        for (int cg = 0; cg < 2; cg++) {
          const uint2 u = __ldg((const uint2*)(P.shift_k + (16 * cl + 8 * cg + g) * 4));
          tap[cg][0] = __byte_perm(u.x, 0, 0x1010); tap[cg][1] = __byte_perm(u.x, 0, 0x3232);
          tap[cg][2] = __byte_perm(u.y, 0, 0x1010); tap[cg][3] = __byte_perm(u.y, 0, 0x3232);
        }
        __nanosleep(HDELAY);
        if (hw == 0 && lane == 0) {
          *(volatile unsigned*)(smem + OFF_EPOCH) = epoch;
          mbar_expect(BAR(B_XRAW), 32768);
          mbar_expect(BAR(B_Y), 32768 + 64);
          mbar_expect(BAR(B_XT), 10240);
          bulk_ld(sb + OFF_F2F, c_img, 10240, BAR(B_XT));
        }
        if (lane == 0) STAMP(3, hw);
        const uint32_t xo = sb + OFF_XT + g * XT_STRIDE + rank * 2048 + q * 4;
        const int krow = 8 + (lane & 7) - (lane >> 3);
        const uint32_t ka = stg + krow * 32 + ((krow & 4) << 2), va = stg + 2304 + lane * 32 + ((lane & 4) << 2);
#pragma unroll 1
        for (int ci = hw; ci < 16; ci += 3) {
          if (lane == 0) {
            mbar_expect(sbar, 2304 + 2048);
            tma2d(stg, &P.tmK, 16 * cl, 1024 * rank + 64 * ci - 8, sbar);
            tma2d(stg + 2304, &P.tmV, 16 * cl, 1024 * rank + 64 * ci, sbar);
          }
          mbar_wait(sbar, ph);
          ph ^= 1;
#pragma unroll 1
          for (int grp = 0; grp < 2; grp++) {
#pragma unroll
            for (int cg = 0; cg < 2; cg++) {
              const uint32_t dst = mapa(xo + (ci >> 3) * 1024 + ((ci & 7) * 4 + 2 * grp) * 16, cg), xbar = mapa(BAR(B_XRAW), cg);
              uint32_t vv[4];
              ldsm4t(vv, (va ^ (cg * 16)) + grp * 1024);
#pragma unroll
              for (int rg = 0; rg < 4; rg++) {
                uint32_t kk[4];
                ldsm4t(kk, (ka ^ (cg * 16)) + grp * 1024 + rg * 256);
                const uint32_t s = hadd(hadd(hadd(hmul(kk[3], tap[cg][3]), hmul(kk[2], tap[cg][2])), hmul(kk[1], tap[cg][1])), hmul(kk[0], tap[cg][0]));
                st_async(dst + (rg & 1) * 512 + (rg >> 1) * 16, hmul(s, vv[rg]), xbar);
              }
            }
          }
          __syncwarp();
        }
      }
      if (lane == 0) {
        STAMP(3, 3 + hw);
#pragma unroll 1
        for (int b = 0; b < 2; b++) {
          mbar_expect(sbar + 8 * b, 2048);
          tma3d(stg + b * 2048, &P.tmQ, 16 * cl, 64 * rank, 2 * (hw + 3 * b), sbar + 8 * b);
        }
      }
      mbar_wait(BAR(B_XRAW), 0);
#pragma unroll 1
      for (int job = hw; job < 16; job += 3) {
        const bool isH = job >= 8;
        const int c = isH ? 4 * (job & 1) + ((job & 7) >> 1) : job;
        const uint32_t lo = (lane >> 4) * 512 + (lane & 15) * 16;
        uint8_t* dst = smem + lo + (isH ? OFF_H + (c & 2) * 8192 + (c >> 2) * 8192 + (c & 1) * 4096 : OFF_XT + c * XT_STRIDE);
        const uint8_t* src0 = isH ? (const uint8_t*)(P.h + (blockIdx.x * 8 + c) * 2048) + (lane & 15) * 32 + (lane >> 4) * 16 : dst;
        const uint8_t* src1 = src0 + (isH ? 512 : 256);
        uint32_t v[32];
#pragma unroll
        for (int i = 0; i < 8; i++) {
          const uint4 u = *(const uint4*)(((i & 1) ? src1 : src0) + (i >> 1) * 1024);
          v[4 * i] = u.x; v[4 * i + 1] = u.y; v[4 * i + 2] = u.z; v[4 * i + 3] = u.w;
        }
        float f0 = __uint_as_float(v[0] << 16);
        if (isH && lane == 0) f0 += __bfloat162float(P.D[blockIdx.x * 8 + c]);
        uint32_t m = __float_as_uint(f0) >> 16;
#pragma unroll
        for (int i = 0; i < 32; i++) asm("max.xorsign.abs.bf16x2 %0, %0, %1;" : "+r"(m) : "r"(v[i]));
        const int e = min(max((int)(__reduce_max_sync(~0u, max(m & 0x7FFFu, (m >> 16) & 0x7FFFu)) >> 7), 1), 253);
        const float sc = __uint_as_float((254 - e) << 23);
#pragma unroll
        for (int i = 0; i < 32; i++)
          asm("cvt.rn.f16x2.f32 %0, %1, %2;" : "=r"(v[i]) : "f"(__uint_as_float(v[i] & 0xFFFF0000u) * sc), "f"((i ? __uint_as_float(v[i] << 16) : f0) * sc));
        if (isH) {
          mbar_wait(BAR(B_XT), 0);
          if (lane < 2) st_async(mapa(sb + OFF_SCALE + (8 * rank + c) * 4, lane), min(max(e + smem[OFF_EX + c] - 124, 1), 254) << 23, mapa(BAR(B_Y), lane));
          mbar_wait(BAR(B_S1FREE), 0);
        } else if (lane == 0) smem[OFF_EX + c] = e;
#pragma unroll
        for (int i = 0; i < 8; i++)
          *(uint4*)(dst + (i >> 1) * 1024 + (i & 1) * 256) = make_uint4(v[4 * i], v[4 * i + 1], v[4 * i + 2], v[4 * i + 3]);
        fence_async();
        __syncwarp();
        if (lane == 0) mbar_arrive(BAR(isH ? B_H + (c & 3) : B_XT));
      }
      if (lane == 0) STAMP(3, 13 + hw);
      mbar_wait(BAR(B_PKFREE), 0);
      {
        const int pi = hw < 2 ? 64 * mb + 32 * hw + lane : 512 + 2 * mb + (lane & 1);
        uint4 f[8];
        int n = 0;
        uint32_t bad;
        do {
          bad = 0;
#pragma unroll
          for (int p = 0; p < 8; p++) f[p] = ld_rlx4(&g_part[hp][p][4 * pi]);
#pragma unroll
          for (int p = 0; p < 8; p++) bad |= stale(f[p], tag);
          if (++n > SPIN_LIMIT) __trap();
        } while (__any_sync(~0u, bad & 1));
        float s0 = 0.f, s1 = 0.f, s2 = 0.f, s3 = 0.f;
#pragma unroll
        for (int p = 0; p < 8; p++) { s0 += __uint_as_float(f[p].x); s1 += __uint_as_float(f[p].y); s2 += __uint_as_float(f[p].z); s3 += __uint_as_float(f[p].w); }
        if (hw < 2 || lane < 2) st_tag4(&g_kv[hp][4 * pi], s0, s1, s2, s3, tag);
      }
      if (lane == 0 && hw == 0) STAMP(3, 8);
      if (hw == 2) {
        mbar_wait(BAR(B_ODONE), 0);
        if (lane < 2) {
          asm volatile("fence.acq_rel.gpu;" ::: "memory");
          asm volatile("red.relaxed.gpu.global.add.u32 [%0], 1;" ::"l"(&g_ocnt[(2 * mb + lane) * 32]) : "memory");
        }
        if (lane == 0) STAMP(3, 7);
        __syncwarp();
      } else {
        const int t = hw * 32 + lane;
        uint4 f[8];
        uint32_t zf, bad;
        int n = 0;
        do {
          asm volatile("ld.relaxed.gpu.global.u32 %0, [%1];" : "=r"(zf) : "l"(&g_kv[hp][2048 + t]) : "memory");
#pragma unroll
          for (int p = 0; p < 8; p++) f[p] = ld_rlx4(&g_kv[hp][4 * ((p & 3) * 128 + (p >> 2) * 64 + t)]);
          bad = zf ^ tag;
#pragma unroll
          for (int p = 0; p < 8; p++) bad |= stale(f[p], tag);
          if (++n > SPIN_LIMIT) __trap();
        } while (__any_sync(~0u, bad & 1));
#define PK2U(a, b) pk2(__uint_as_float(a), __uint_as_float(b))
#pragma unroll
        for (int hh = 0; hh < 2; hh++) {
          const uint4* ff = &f[4 * hh];
          uint8_t* dst = smem + OFF_KVB + hh * 2560 + q * 512 + (16 * hw + g) * 16;
          *(uint4*)dst = make_uint4(PK2U(ff[0].x, ff[0].y), PK2U(ff[1].x, ff[1].y), PK2U(ff[2].x, ff[2].y), PK2U(ff[3].x, ff[3].y));
          *(uint4*)(dst + 128) = make_uint4(PK2U(ff[0].z, ff[0].w), PK2U(ff[1].z, ff[1].w), PK2U(ff[2].z, ff[2].w), PK2U(ff[3].z, ff[3].w));
        }
        const uint32_t zz = PK2U(zf, zf);
        *(uint4*)(smem + OFF_KVB + hw * 2560 + 2048 + lane * 16) = make_uint4(zz, zz, zz, zz);
        fence_async();
        __syncwarp();
        if (lane == 0) { mbar_arrive(BAR(B_KV)); if (hw == 0) STAMP(3, 9); }
      }
      mbar_wait(BAR(B_Y), 0);
      {
        const float2 sc0 = *(const float2*)(smem + OFF_SCALE + 8 * q), sc1 = *(const float2*)(smem + OFF_SCALE + 32 + 8 * q);
        const uint32_t yl = sb + OFF_XT + (lane & 7) * XT_STRIDE + (lane >> 3) * 16;
        int phs = ph, b = 0;
#pragma unroll 1
        for (int ci = hw; ci < 16; ci += 3) {
          const uint32_t qb = stg + b * 2048;
          mbar_wait(sbar + 8 * b, (phs >> b) & 1);
          phs ^= 1 << b;
#pragma unroll 1
          for (int nl = 0; nl < 2; nl++)
#pragma unroll
            for (int cg = 0; cg < 2; cg++) {
              uint32_t yy[4], qq[4];
              const uint32_t qa = ((qb + lane * 32 + ((lane & 4) << 2)) ^ (cg * 16)) + nl * 1024;
              ldsm4t(yy, yl + cg * 2048 + (2 * ci + nl) * 64);
              ldsm4(qq, qa);
              const float2 sc = cg ? sc1 : sc0;
#pragma unroll
              for (int m = 0; m < 4; m++) {
                const float2 f = __half22float2(*(const __half2*)&yy[m]);
                qq[m] = hmul(qq[m], pk2(f.x * sc.x, f.y * sc.y));
              }
              stsm4(qa, qq[0], qq[1], qq[2], qq[3]);
            }
          fence_async();
          __syncwarp();
          if (lane == 0) {
            tma3d_st(&P.tmOA, qb, 16 * cl, 64 * rank + 32 * (ci >> 3), 2 * (ci & 7));
            asm volatile("cp.async.bulk.commit_group;\ncp.async.bulk.wait_group.read 0;" ::: "memory");
            if (ci + 6 < 16) {
              mbar_expect(sbar + 8 * b, 2048);
              tma3d(qb, &P.tmQ, 16 * cl, 64 * rank + 32 * ((ci + 6) >> 3), 2 * ((ci + 6) & 7), sbar + 8 * b);
            }
          }
          b ^= 1;
        }
      }
      if (lane == 0) STAMP(3, 10 + hw);
    }
  }
}

typedef CUresult (*EncodeFn)(CUtensorMap*, CUtensorMapDataType, cuuint32_t, void*, const cuuint64_t*, const cuuint64_t*,
                             const cuuint32_t*, const cuuint32_t*, CUtensorMapInterleave, CUtensorMapSwizzle,
                             CUtensorMapL2promotion, CUtensorMapFloatOOBfill);

static void enc(EncodeFn fn, CUtensorMap* m, const void* p, int rank, const cuuint64_t* dims, const cuuint64_t* strides,
                const cuuint32_t* box, CUtensorMapSwizzle swz, CUtensorMapL2promotion promo) {
  cuuint32_t es[3] = {1, 1, 1};
  fn(m, CU_TENSOR_MAP_DATA_TYPE_BFLOAT16, rank, (void*)p, dims, strides, box, es, CU_TENSOR_MAP_INTERLEAVE_NONE, swz, promo,
     CU_TENSOR_MAP_FLOAT_OOB_FILL_NONE);
}

extern "C" void kernel_launch(void* const* d_in, const int* in_sizes, int n_in, void* d_out, int out_size) {
  void* fp = nullptr;
  cudaDriverEntryPointQueryResult qr;
  cudaGetDriverEntryPoint("cuTensorMapEncodeTiled", &fp, cudaEnableDefault, &qr);
  EncodeFn fn = (EncodeFn)fp;
  Params P;
  P.shift_k = (const __nv_bfloat16*)d_in[3]; P.h = (const __nv_bfloat16*)d_in[4]; P.D = (const __nv_bfloat16*)d_in[5];
  const CUtensorMapSwizzle S128 = CU_TENSOR_MAP_SWIZZLE_128B, S32 = CU_TENSOR_MAP_SWIZZLE_32B;
  const CUtensorMapL2promotion P0 = CU_TENSOR_MAP_L2_PROMOTION_NONE, P128 = CU_TENSOR_MAP_L2_PROMOTION_L2_128B;
  { cuuint64_t d[2] = {1024, 2048}, s[1] = {2048}; cuuint32_t b[2] = {64, 128}; enc(fn, &P.tmX, d_in[6], 2, d, s, b, S128, P128); }
  { cuuint64_t d[3] = {1024, 1024, 3}, s[2] = {6144, 2048}; cuuint32_t b[3] = {64, 64, 3}; enc(fn, &P.tmW, d_in[7], 3, d, s, b, S128, P128); }
  { cuuint64_t d[3] = {64, 1024, 16}, s[2] = {2048, 128}; cuuint32_t b[3] = {64, 64, 2}; enc(fn, &P.tmWo, d_in[8], 3, d, s, b, S128, P128); }
  { cuuint64_t d[2] = {1024, 2048}, s[1] = {2048}; cuuint32_t b[2] = {16, 72}; enc(fn, &P.tmK, d_in[1], 2, d, s, b, S32, P0); }
  { cuuint64_t d[2] = {1024, 2048}, s[1] = {2048}; cuuint32_t b[2] = {16, 64}; enc(fn, &P.tmV, d_in[2], 2, d, s, b, S32, P0); }
  { cuuint64_t d[3] = {1024, 128, 16}, s[2] = {32768, 2048}; cuuint32_t b[3] = {16, 32, 2}; enc(fn, &P.tmQ, d_in[0], 3, d, s, b, S32, P0); }
  { cuuint64_t d[3] = {1024, 128, 16}, s[2] = {65536, 4096}; cuuint32_t b[3] = {16, 32, 2}; enc(fn, &P.tmOA, d_out, 3, d, s, b, S32, P0); }
  { cuuint64_t d[2] = {2048, 2048}, s[1] = {4096}; cuuint32_t b[2] = {64, 64}; enc(fn, &P.tmOB, d_out, 2, d, s, b, S128, P0); }
  cudaFuncSetAttribute(fused_kernel, cudaFuncAttributeMaxDynamicSharedMemorySize, SMEM_TOTAL);
  fused_kernel<<<128, 384, SMEM_TOTAL>>>(P);
}
```

```cpp
#include <cuda_runtime.h>
#include <cuda_bf16.h>
#include <cuda_fp16.h>
#include <cuda.h>
#include <stdint.h>

template<int TA, int TB, int SA=1> __device__ __forceinline__ void wgmma_ss_n192(float (&d)[96], uint64_t da, uint64_t db, int scale_d) {
  asm volatile("{\n.reg .pred p;\nsetp.ne.b32 p, %98, 0;\n"
    "wgmma.mma_async.sync.aligned.m64n192k16.f32.bf16.bf16 {%0, %1, %2, %3, %4, %5, %6, %7, %8, %9, %10, %11, %12, %13, %14, %15, %16, %17, %18, %19, %20, %21, %22, %23, %24, %25, %26, %27, %28, %29, %30, %31, %32, %33, %34, %35, %36, %37, %38, %39, %40, %41, %42, %43, %44, %45, %46, %47, %48, %49, %50, %51, %52, %53, %54, %55, %56, %57, %58, %59, %60, %61, %62, %63, %64, %65, %66, %67, %68, %69, %70, %71, %72, %73, %74, %75, %76, %77, %78, %79, %80, %81, %82, %83, %84, %85, %86, %87, %88, %89, %90, %91, %92, %93, %94, %95}, %96, %97, p, %101, 1, %99, %100;\n}\n"
    : "+f"(d[0]), "+f"(d[1]), "+f"(d[2]), "+f"(d[3]), "+f"(d[4]), "+f"(d[5]), "+f"(d[6]), "+f"(d[7]), "+f"(d[8]), "+f"(d[9]), "+f"(d[10]), "+f"(d[11]), "+f"(d[12]), "+f"(d[13]), "+f"(d[14]), "+f"(d[15]), "+f"(d[16]), "+f"(d[17]), "+f"(d[18]), "+f"(d[19]), "+f"(d[20]), "+f"(d[21]), "+f"(d[22]), "+f"(d[23]), "+f"(d[24]), "+f"(d[25]), "+f"(d[26]), "+f"(d[27]), "+f"(d[28]), "+f"(d[29]), "+f"(d[30]), "+f"(d[31]), "+f"(d[32]), "+f"(d[33]), "+f"(d[34]), "+f"(d[35]), "+f"(d[36]), "+f"(d[37]), "+f"(d[38]), "+f"(d[39]), "+f"(d[40]), "+f"(d[41]), "+f"(d[42]), "+f"(d[43]), "+f"(d[44]), "+f"(d[45]), "+f"(d[46]), "+f"(d[47]), "+f"(d[48]), "+f"(d[49]), "+f"(d[50]), "+f"(d[51]), "+f"(d[52]), "+f"(d[53]), "+f"(d[54]), "+f"(d[55]), "+f"(d[56]), "+f"(d[57]), "+f"(d[58]), "+f"(d[59]), "+f"(d[60]), "+f"(d[61]), "+f"(d[62]), "+f"(d[63]), "+f"(d[64]), "+f"(d[65]), "+f"(d[66]), "+f"(d[67]), "+f"(d[68]), "+f"(d[69]), "+f"(d[70]), "+f"(d[71]), "+f"(d[72]), "+f"(d[73]), "+f"(d[74]), "+f"(d[75]), "+f"(d[76]), "+f"(d[77]), "+f"(d[78]), "+f"(d[79]), "+f"(d[80]), "+f"(d[81]), "+f"(d[82]), "+f"(d[83]), "+f"(d[84]), "+f"(d[85]), "+f"(d[86]), "+f"(d[87]), "+f"(d[88]), "+f"(d[89]), "+f"(d[90]), "+f"(d[91]), "+f"(d[92]), "+f"(d[93]), "+f"(d[94]), "+f"(d[95])
    : "l"(da), "l"(db), "r"(scale_d), "n"(TA), "n"(TB), "n"(SA));
}
template<int TA, int TB, int SA=1> __device__ __forceinline__ void wgmma_ss_n128(float (&d)[64], uint64_t da, uint64_t db, int scale_d) {
  asm volatile("{\n.reg .pred p;\nsetp.ne.b32 p, %66, 0;\n"
    "wgmma.mma_async.sync.aligned.m64n128k16.f32.bf16.bf16 {%0, %1, %2, %3, %4, %5, %6, %7, %8, %9, %10, %11, %12, %13, %14, %15, %16, %17, %18, %19, %20, %21, %22, %23, %24, %25, %26, %27, %28, %29, %30, %31, %32, %33, %34, %35, %36, %37, %38, %39, %40, %41, %42, %43, %44, %45, %46, %47, %48, %49, %50, %51, %52, %53, %54, %55, %56, %57, %58, %59, %60, %61, %62, %63}, %64, %65, p, %69, 1, %67, %68;\n}\n"
    : "+f"(d[0]), "+f"(d[1]), "+f"(d[2]), "+f"(d[3]), "+f"(d[4]), "+f"(d[5]), "+f"(d[6]), "+f"(d[7]), "+f"(d[8]), "+f"(d[9]), "+f"(d[10]), "+f"(d[11]), "+f"(d[12]), "+f"(d[13]), "+f"(d[14]), "+f"(d[15]), "+f"(d[16]), "+f"(d[17]), "+f"(d[18]), "+f"(d[19]), "+f"(d[20]), "+f"(d[21]), "+f"(d[22]), "+f"(d[23]), "+f"(d[24]), "+f"(d[25]), "+f"(d[26]), "+f"(d[27]), "+f"(d[28]), "+f"(d[29]), "+f"(d[30]), "+f"(d[31]), "+f"(d[32]), "+f"(d[33]), "+f"(d[34]), "+f"(d[35]), "+f"(d[36]), "+f"(d[37]), "+f"(d[38]), "+f"(d[39]), "+f"(d[40]), "+f"(d[41]), "+f"(d[42]), "+f"(d[43]), "+f"(d[44]), "+f"(d[45]), "+f"(d[46]), "+f"(d[47]), "+f"(d[48]), "+f"(d[49]), "+f"(d[50]), "+f"(d[51]), "+f"(d[52]), "+f"(d[53]), "+f"(d[54]), "+f"(d[55]), "+f"(d[56]), "+f"(d[57]), "+f"(d[58]), "+f"(d[59]), "+f"(d[60]), "+f"(d[61]), "+f"(d[62]), "+f"(d[63])
    : "l"(da), "l"(db), "r"(scale_d), "n"(TA), "n"(TB), "n"(SA));
}
template<int TA, int TB, int SA=1> __device__ __forceinline__ void wgmma_ss_n72(float (&d)[36], uint64_t da, uint64_t db, int scale_d) {
  asm volatile("{\n.reg .pred p;\nsetp.ne.b32 p, %38, 0;\n"
    "wgmma.mma_async.sync.aligned.m64n72k16.f32.bf16.bf16 {%0, %1, %2, %3, %4, %5, %6, %7, %8, %9, %10, %11, %12, %13, %14, %15, %16, %17, %18, %19, %20, %21, %22, %23, %24, %25, %26, %27, %28, %29, %30, %31, %32, %33, %34, %35}, %36, %37, p, %41, 1, %39, %40;\n}\n"
    : "+f"(d[0]), "+f"(d[1]), "+f"(d[2]), "+f"(d[3]), "+f"(d[4]), "+f"(d[5]), "+f"(d[6]), "+f"(d[7]), "+f"(d[8]), "+f"(d[9]), "+f"(d[10]), "+f"(d[11]), "+f"(d[12]), "+f"(d[13]), "+f"(d[14]), "+f"(d[15]), "+f"(d[16]), "+f"(d[17]), "+f"(d[18]), "+f"(d[19]), "+f"(d[20]), "+f"(d[21]), "+f"(d[22]), "+f"(d[23]), "+f"(d[24]), "+f"(d[25]), "+f"(d[26]), "+f"(d[27]), "+f"(d[28]), "+f"(d[29]), "+f"(d[30]), "+f"(d[31]), "+f"(d[32]), "+f"(d[33]), "+f"(d[34]), "+f"(d[35])
    : "l"(da), "l"(db), "r"(scale_d), "n"(TA), "n"(TB), "n"(SA));
}
template<int TB, int SA=1> __device__ __forceinline__ void wgmma_rs_n40(float (&d)[20], uint32_t a0, uint32_t a1, uint32_t a2, uint32_t a3, uint64_t db, int scale_d) {
  asm volatile("{\n.reg .pred p;\nsetp.ne.b32 p, %25, 0;\n"
    "wgmma.mma_async.sync.aligned.m64n40k16.f32.bf16.bf16 {%0, %1, %2, %3, %4, %5, %6, %7, %8, %9, %10, %11, %12, %13, %14, %15, %16, %17, %18, %19}, {%20, %21, %22, %23}, %24, p, %27, 1, %26;\n}\n"
    : "+f"(d[0]), "+f"(d[1]), "+f"(d[2]), "+f"(d[3]), "+f"(d[4]), "+f"(d[5]), "+f"(d[6]), "+f"(d[7]), "+f"(d[8]), "+f"(d[9]), "+f"(d[10]), "+f"(d[11]), "+f"(d[12]), "+f"(d[13]), "+f"(d[14]), "+f"(d[15]), "+f"(d[16]), "+f"(d[17]), "+f"(d[18]), "+f"(d[19])
    : "r"(a0), "r"(a1), "r"(a2), "r"(a3), "l"(db), "r"(scale_d), "n"(TB), "n"(SA));
}
template<int TB> __device__ __forceinline__ void wgmma_hrs_n64(uint32_t (&d)[16], uint32_t a0, uint32_t a1, uint32_t a2, uint32_t a3, uint64_t db, int scale_d) {
  asm volatile("{\n.reg .pred p;\nsetp.ne.b32 p, %21, 0;\n"
    "wgmma.mma_async.sync.aligned.m64n64k16.f16.f16.f16 {%0, %1, %2, %3, %4, %5, %6, %7, %8, %9, %10, %11, %12, %13, %14, %15}, {%16, %17, %18, %19}, %20, p, 1, 1, %22;\n}\n"
    : "+r"(d[0]), "+r"(d[1]), "+r"(d[2]), "+r"(d[3]), "+r"(d[4]), "+r"(d[5]), "+r"(d[6]), "+r"(d[7]), "+r"(d[8]), "+r"(d[9]), "+r"(d[10]), "+r"(d[11]), "+r"(d[12]), "+r"(d[13]), "+r"(d[14]), "+r"(d[15])
    : "r"(a0), "r"(a1), "r"(a2), "r"(a3), "l"(db), "r"(scale_d), "n"(TB));
}
template<int TB> __device__ __forceinline__ void wgmma_hrs_n32(uint32_t (&d)[8], uint32_t a0, uint32_t a1, uint32_t a2, uint32_t a3, uint64_t db, int scale_d) {
  asm volatile("{\n.reg .pred p;\nsetp.ne.b32 p, %13, 0;\n"
    "wgmma.mma_async.sync.aligned.m64n32k16.f16.f16.f16 {%0, %1, %2, %3, %4, %5, %6, %7}, {%8, %9, %10, %11}, %12, p, 1, 1, %14;\n}\n"
    : "+r"(d[0]), "+r"(d[1]), "+r"(d[2]), "+r"(d[3]), "+r"(d[4]), "+r"(d[5]), "+r"(d[6]), "+r"(d[7])
    : "r"(a0), "r"(a1), "r"(a2), "r"(a3), "l"(db), "r"(scale_d), "n"(TB));
}

__device__ __align__(128) const uint32_t c_thr[1536] = {
  0x33fb33ff,0xa49c9de4,0x33273352,0xaf2cae76,0x33e233f1,0xa96ca7bd,0x32c432f7,0xb045afdd,0x33b733cf,0xac3eaaf7,0x3250328c,0xb0eab099,
  0x3378339a,0xadbcacff,0x31cd3211,0xb182b137,0x33d033fb,0xaadea46a,0x299e2d17,0xb3e0b396,0x32fb337a,0xafd2adb1,0xa78b1f76,0xb3f2b3ff,
  0x318b3254,0xb1c5b0e5,0xae6bac32,0xb354b3b8,0x2f4230a3,0xb321b285,0xb133b040,0xb215b2c7,0x337c33f2,0xada5a759,0xb179afc8,0xb1d6b2fe,
  0x31463293,0xb204b08e,0xb394b2ba,0xad23b055,0x2b402f4e,0xb3cbb31e,0xb3e4b3f9,0x293ba533,0xac269c52,0xb3bab400,0xb258b357,0x30e02e5f,
  0x330133e5,0xafbda922,0xb3f3b3c9,0x2727ab59,0x2deb314a,0xb36fb200,0xb194b32f,0x31bc2f0a,0xacdb2084,0xb39fb3ff,0xa565aea4,0x33f93347,
  0xb2b6b0db,0xb05ab25c,0x30892c1a,0x329733bc,0x326033d4,0xb0d6aa94,0xb00ab29b,0x32e83084,0x20e82f64,0xb3feb318,0x2d8da597,0x338133f8,
  0xb1fcae48,0xb14fb35c,0x339031b8,0x2d3a3199,0xb3e6b3ae,0x2909ac7b,0x32d133f4,0xb030a6f5,0x319d33bf,0xb1b3ac02,0x2e3ca874,0x335e33ec,
  0xacc32b89,0xb3a3b3c6,0x33f83276,0x25c930b7,0xb3dcb1f8,0xaa01b154,0x30653335,0xb2b0aef4,0xb107b383,0x32392d81,0xafa6214d,0xb307b3fe,
  0x30bc33a5,0xb273acb7,0x33c5311b,0x2ba23229,0xb0cc94b6,0xb267b400,0x30153360,0xb2e1ae31,0xb385b3ab,0x2d76ac93,0xb166a691,0xb1e7b3f5,
  0x22deb06a,0x33fd32ac,0xb337b3da,0x2ee8aa19,0x2f853387,0xb310ad6a,0x322d33fe,0xb1162216,0xb2a9abd3,0xb06fb3c2,0xb07428a6,0xb2a5b3ea,
  0xb111b3e9,0x323128be,0xb30db3c3,0x2f90abba,0x31aa227a,0x31a633fd,0x2e25ad5e,0x33633389,0x2d6a3365,0xb387ae1a,0xa21631aa,0xb3feb1a6,
  0xb3c2af85,0xabd3b310,0xb3eab22d,0x28a6b116,0xa8beb2a9,0x33e9306f,0x2bbab074,0x33c332a5,0x33fd3111,0x227a3231,0x3389330d,0xad5e2f90,
  0x2a63333f,0xb3d7aec6,0xb2a2a1b1,0xb07ab3fe,0xb3f7b158,0x25fbb1f4,0xacb7b38b,0x33a52d52,0x2e0eb025,0x336832d8,0x340030bc,0x14b63273,
  0x323533c0,0xb10c2beb,0xac9330cc,0xb3abb267,0x23433316,0xb3fdaf6f,0xb38eb225,0x2d46b11f,0xb342b29e,0x2ebbb07f,0x31e3aa7c,0x316b33d6,
  0x3264a6c3,0x30d133f5,0x2c0233ac,0xb3bfac87,0x28f0336a,0xb3e7ae02,0xb3c6b19d,0x2b89b1b3,0xa59732e8,0xb3f8b00a,0xaccfb3ed,0x33a1285b,
  0xb1b8b381,0x3199ad8d,0x336c31df,0xadf73170,0x33f42d3a,0x26f53390,0xb30423a7,0xafb2b3fc,0xb05f3030,0xb2b3b2d1,0x29e8b27a,0x33dd30b2,
  0xab5932b6,0xb3c9b05a,0x30adb089,0x327e3297,0xaf0ab3f3,0x332fa727,0x240633b0,0xb3fcac6f,0x33473194,0xaea431bc,0xb174b359,0x31daae54,
  0xb3bca565,0xac1ab3f9,0x33ee2f59,0xa842331b,0xaddf3281,0xb371b0a8,0x34002b40,0x1c5233cb,0xa759b3ef,0x33f22829,0xb2fe2c26,0xafc8b3ba,
  0x308e337c,0xb2932da5,0x3055b179,0x32ba31d6,0xb31eb146,0x2f4eb204,0xa5333394,0xb3f9ad23,0xaff33249,0xb2f1b0f3,0x30e532fb,0xb2542fd2,
  0x2b28b373,0x33cc2dd4,0xb285b18b,0x30a3b1c5,0x246a33fa,0xb3fba500,0x33962f42,0xad173321,0xadb1b3d0,0x337aaade,0xb3ffa99e,0x1f76b3e0,
  0xb0ee320d,0xb24db13c,0xac4b3398,0xb3b5ad0b,0x304ab289,0x32c1309e,0x2985b3ce,0x33e12b0f,0xaf3732f4,0xb324afe8,0xa4ce33f0,0xb3faa7ef,
  0x2dc8b34f,0x33762e82,0x9de4b3ff,0x33ff1ead,0xb1c931cd,0xb186b182,0xb3762e82,0xadc8b34f,0x324db13c,0x30ee320d,0x33b5ad0b,0x2c4b3398,
  0xb2c1309e,0xb04ab289,0xb3e12b0f,0xa985b3ce,0x3324afe8,0x2f3732f4,0x33faa7ef,0x24ce33f0,0xb285318b,0xb0a3b1c5,0xb2c7ae6b,0x3040b354,
  0x3396af42,0x2d173321,0x31413133,0xb2093215,0xb3ff299e,0x9f76b3e0,0xae8db2bd,0x334cb050,0x33b8278b,0xac3233f2,0x281033b3,0xb3ef2c57,
  0xb31e3146,0xaf4eb204,0xa533b394,0x33f9ad23,0x3400ab40,0x9c5233cb,0xae5f33e4,0xb357a93b,0xb2feac26,0x2fc8b3ba,0x3245b258,0x30f830e0,
  0x30553179,0xb2ba31d6,0xb3df2e99,0xa9b6b34a,0xb39230fd,0xad2fb241,0x3200b301,0x314a2fbd,0x337f1b11,0xad993400,0xb3ff2deb,0xa084b36f,
  0xb005b129,0x32ebb21d,0x325c2cdb,0xb0db339f,0xa92233de,0xb3e529cf,0xab59b2b6,0x33c9b05a,0xb3dd30b2,0xa9e8b27a,0x33d4ab71,0xaa9433c8,
  0x32212c0e,0xb12433bd,0xaf64b0d6,0x3318b260,0x197fb345,0x3400aeaf,0xae4833fe,0xb35c20e8,0xb23d3332,0xb102aeff,0x33aeb14f,0x2c7b31fc,
  0xb3fe3065,0xa14db2b0,0x2ebb307f,0xb342329e,0x300f2fa6,0xb2e53307,0x30d1b3f5,0x326426c3,0x302ab400,0x32d517db,0xb3e72e02,0x28f0b36a,
  0xb3fd2f6f,0x2343b316,0x2d46311f,0xb38e3225,0xb3f53015,0x2691b2e1,0xaf9b33eb,0xb30a288d,0x2a193166,0xb3da31e7,0x33d7aec6,0xaa63333f,
  0x3313b337,0x2f7a2ee8,0xa5fbb1f4,0x33f7b158,0xb1a1a8d7,0x31afb3e8,0xb36832d8,0xae0eb025,0xb3c22f85,0x2bd3b310,0xb3ea322d,0xa8a6b116,
  0xa8be32a9,0xb3e9306f,0x2bba3074,0xb3c332a5,0x33fdb111,0xa27a3231,0x3389b30d,0x2d5e2f90,0xa216b1aa,0x33feb1a6,0xaed2ae25,0x333db363,
  0xb3652edd,0x2e1ab33a,0xb1aa227a,0x31a6b3fd,0xaf853387,0xb3102d6a,0xb22d33fe,0xb116a216,0x32a9abd3,0xb06f33c2,0x307428a6,0xb2a533ea,
  0x3111b3e9,0x3231a8be,0x330db3c3,0x2f902bba,0xb2e12e31,0x3015b360,0x288db1a1,0x33ebb1af,0xb1e733f5,0xb1662691,0xb33f2f9b,0x2ec6b30a,
  0x2ee82a19,0xb33733da,0xb15833d7,0xb1f42a63,0x33e8b313,0x28d72f7a,0x302525fb,0xb2d833f7,0xb2392d81,0x3107b383,0x3307b3fe,0x2fa6214d,
  0xb35e33ec,0xae3ca874,0x97dbb00f,0x3400b2e5,0xa5c930b7,0xb3f83276,0xb316302a,0x2f6fb2d5,0x32b0aef4,0xb0653335,0xb29e33fd,0xb07f2343,
  0xb1702ccf,0x31dfb3a1,0x3345b124,0xaeaf3221,0xb3fc336c,0xa3a7adf7,0x3332b400,0x2eff997f,0xb0b23304,0xb27a2fb2,0x2b71b102,0x33c8b23d,
  0x2c0e29e8,0xb3bd33dd,0xb0d62a94,0x3260b3d4,0xb0892c1a,0x3297b3bc,0x2aad2842,0xb3d333ee,0xb3b0327e,0x2c6fb0ad,0x3241b035,0xb0fd32ce,
  0xb35933fc,0xae542406,0x3400b392,0x1b112d2f,0xaf5931da,0xb31b3174,0x321db37f,0x3129ad99,0xaf152ac6,0x332cb3d2,0xb1463293,0xb204308e,
  0xb281312e,0x30a8b219,0xab402f4e,0xb3cb331e,0xb3ef3371,0x2829addf,0x2c269c52,0xb3ba3400,0xb37c33f2,0xada52759,0x3179afc8,0xb1d632fe,
  0xacf32953,0x339cb3e3,0xb3fa33cc,0x2500ab28,0xb0942f21,0x3290b32a,0xb3d033fb,0xaade246a,0xb249317d,0x30f3b1d2,0xb2fb337a,0xafd22db1,
  0xb37332f1,0x2dd4aff3,0xb18b3254,0xb1c530e5,0xa96c27bd,0x33e2b3f1,0xb0452fdd,0x32c4b2f7,0xac3e2af7,0x33b7b3cf,0xb0ea3099,0x3250b28c,
  0xadbc2cff,0x3378b39a,0xb1823137,0x31cdb211,0xaf2c2e76,0x3327b352,0xb20d31c9,0x313cb186,0x313c3186,0xb20db1c9,0x2d0b2dc8,0xb398b376,
  0x309e30ee,0xb289b24d,0x2b0f2c4b,0xb3ceb3b5,0x2fe8304a,0xb2f4b2c1,0x27ef2985,0xb3f0b3e1,0x2e822f37,0xb34fb324,0x1ead24ce,0xb3ffb3fa,
  0xb2bdb209,0xb050b141,0xb290b32a,0x30942f21,0xb3b3b34c,0xac57ae8d,0xb0f3b1d2,0x3249317d,0xb400b3ef,0x1d1ba810,0xadd4aff3,0x337332f1,
  0xb39cb3e3,0x2cf32953,0xa500ab28,0x33fa33cc,0xae99b0f8,0x334a3245,0x33ff33b2,0x201f2c63,0x2438a9b6,0x33fc33df,0x332c33d2,0xaf15aac6,
  0x303a2ce7,0x32cb339e,0x30a83219,0xb281b12e,0x32ee31c0,0x2ffe3190,0x28292ddf,0xb3efb371,0x33b0327e,0x2c6f30ad,0xb241b035,0xb0fdb2ce,
  0x335933fc,0xae54a406,0xb400b392,0x1b11ad2f,0x2f5931da,0xb31bb174,0xb21db37f,0x31292d99,0xaaad2842,0xb3d3b3ee,0xa9cfb005,0x33de32eb,
  0x285b305f,0xb3edb2b3,0x2c0ea9e8,0x33bd33dd,0xb170accf,0xb1dfb3a1,0x33453124,0x2eaf3221,0xb3fcb36c,0x23a7adf7,0x33323400,0xaeff997f,
  0xb0b2b304,0x327a2fb2,0x2b713102,0xb3c8b23d,0xb400b2e5,0x17dbb00f,0x2e023264,0xb36ab0d1,0xaf6fb2d5,0x3316302a,0xb11fa8f0,0xb225b3e7,
  0x307f2343,0x329e33fd,0xb3d6b38e,0x2a7cad46,0x33f53342,0xa6c32ebb,0xac87b1e3,0x33ac316b,0x28d7af7a,0x33e83313,0xb2d8b3f7,0x3025a5fb,
  0x33eb31af,0x288d31a1,0x2bebae0e,0x33c03368,0x2ec6330a,0xb33faf9b,0x33fe3235,0x21b1310c,0xb1f4aa63,0xb158b3d7,0x2d5232a2,0xb38bb07a,
  0x33a7333d,0xacab2ed2,0x33f63162,0x262d31eb,0xaa4b301a,0xb3d8b2de,0x2a32326b,0xb3d9b0c7,0xb3f6b26f,0x265fb0c1,0xb3a9b020,0xac9fb2db,
  0x0e48b15d,0x340031f0,0xae1ab33a,0x33652edd,0xaed22e25,0xb33db363,0xb1eb0e48,0xb162b400,0xb2deb3a7,0x301aacab,0xb0c7b3f6,0x326b262d,
  0x30c1aa4b,0x326f33d8,0x32db2a32,0x302033d9,0x31f033f6,0xb15d265f,0x2edd33a9,0xb33aac9f,0xb2acb385,0x306aad76,0x2a19b166,0x33da31e7,
  0x3229a2de,0x311b33fd,0x33133337,0xaf7a2ee8,0x2e3133c5,0xb360aba2,0xb1a128d7,0xb1afb3e8,0xb3f5b015,0xa691b2e1,0xaf9bb3eb,0x330a288d,
  0x3154acc3,0x31f833a3,0x2ef433f8,0xb335a5c9,0x2d8133dc,0xb383aa01,0xb3feb065,0x214db2b0,0xb3ecb107,0x2874b239,0x300fafa6,0x32e53307,
  0x30b7ae3c,0x3276335e,0x302a3400,0xb2d517db,0x312433bd,0xb2212c0e,0xb318b260,0x2f64b0d6,0xb400aeaf,0x997fb345,0x335c20e8,0x2e4833fe,
  0x3102aeff,0x323d3332,0xac7b31fc,0xb3aeb14f,0x2a9433c8,0xb3d4ab71,0xb084b3e6,0x329ba909,0xb2ce2aad,0xb035b3d3,0x33e529cf,0x292233de,
  0x2d2fb241,0x339230fd,0xb14a2fbd,0xb200b301,0x2d993400,0xb37f1b11,0x2084b36f,0x33ff2deb,0xb2ebb21d,0x3005b129,0x30db339f,0xb25c2cdb,
  0xae5fb3e4,0x3357a93b,0xb190303a,0xb1c0b2cb,0x32453258,0xb0f830e0,0x2c63b2ee,0x33b22ffe,0xb3dfae99,0x29b6b34a,0x2ac633ff,0xb3d2a01f,
  0x339ea438,0x2ce733fc,0xb12eb32c,0x3219af15,0x33b8a78b,0x2c3233f2,0x2810b3b3,0x33ef2c57,0xb2c72e6b,0xb040b354,0x29533400,0xb3e31d1b,
  0x3141b133,0x32093215,0xaf21b39c,0x332aacf3,0xae8d32bd,0xb34cb050,0x317d3290,0xb1d23094,0x27bd33fb,0xb3f1249c,0x2fdd3327,0xb2f72f2c,
  0xaaf7b3e2,0x33cfa96c,0xb099b2c4,0x328cb045,0x2cff33b7,0xb39a2c3e,0x31373250,0xb21130ea,0xae76b378,0x3352adbc,0xb1c9b1cd,0x3186b182,
  0xb3ff1ead,0x1de4b3ff,0xb352adbc,0x2e76b378,0x33f1249c,0xa7bd33fb,0x32f72f2c,0xafdd3327,0xb3cfa96c,0x2af7b3e2,0xb28cb045,0x3099b2c4,
  0x339a2c3e,0xacff33b7,0x321130ea,0xb1373250,0x2953b400,0x33e31d1b,0x33ccadd4,0x2b283373,0xaf21339c,0xb32aacf3,0xb3fb2500,0x246ab3fa,
  0x317db290,0x31d23094,0x337a2ade,0xadb133d0,0xb2f130f3,0xaff3b249,0xb254afd2,0x30e5b2fb,0x339e2438,0xace733fc,0xb12e332c,0xb219af15,
  0xb190b03a,0x31c0b2cb,0x3371b0a8,0x2ddf3281,0x2c6332ee,0xb3b22ffe,0xb3f22829,0x2759b3ef,0x2ac6b3ff,0x33d2a01f,0x32932da5,0xb08e337c,
  0xaf0a33f3,0xb32fa727,0x2406b3b0,0x33fcac6f,0x3347b194,0x2ea431bc,0xb1743359,0xb1daae54,0xb3bc2565,0x2c1ab3f9,0x33eeaf59,0x2842331b,
  0x30ad3089,0xb27e3297,0xb2ceaaad,0x3035b3d3,0xb29ba909,0x3084b3e6,0x305f3030,0xb2b332d1,0x259732e8,0xb3f8300a,0x2ccfb3ed,0x33a1a85b,
  0x31b8b381,0x31992d8d,0xb36c31df,0xadf7b170,0xb3f42d3a,0x26f5b390,0x330423a7,0xafb233fc,0x316bb3d6,0x31e32a7c,0xb3832a01,0x2d81b3dc,
  0xb3bf2c87,0x2c02b3ac,0x28743239,0xb3ec3107,0x2b8931b3,0xb3c6319d,0x3276b35e,0x30b72e3c,0x31f8b3a3,0x31542cc3,0xb33525c9,0x2ef4b3f8,
  0x310c2beb,0xb23533c0,0x33abb267,0x2c9330cc,0x307ab3fe,0x32a2a1b1,0xb06aad76,0x32acb385,0xb3a52d52,0x2cb7b38b,0xb11b33fd,0xb229a2de,
  0x94b63273,0xb40030bc,0x3360aba2,0xae3133c5,0xb2de33a7,0xb01aacab,0xb0c733f6,0xb26b262d,0x30c12a4b,0xb26f33d8,0x32dbaa32,0xb02033d9,
  0x31f0b3f6,0x315d265f,0x2eddb3a9,0x333aac9f,0xb1eb8e48,0x3162b400,0xb3872e1a,0x2d6ab365,0xae25ad5e,0x3363b389,0x8e48b15d,0x3400b1f0,
  0xb3a7333d,0xacabaed2,0xb3f63162,0x262db1eb,0x2a4b301a,0xb3d832de,0xaa32326b,0xb3d930c7,0x33f6b26f,0x265f30c1,0x33a9b020,0xac9f32db,
  0x33c0b368,0x2beb2e0e,0x30cc94b6,0xb2673400,0x21b1b10c,0x33feb235,0x3385b3ab,0x2d762c93,0xb38b307a,0x2d52b2a2,0xa2deb06a,0x33fdb2ac,
  0xb0bc33a5,0xb2732cb7,0xb3c5311b,0x2ba2b229,0x26c32ebb,0xb3f53342,0xb3ac316b,0x2c87b1e3,0x336ab0d1,0xae023264,0xb19d33bf,0xb1b32c02,
  0x3225b3e7,0x311fa8f0,0x2cc32b89,0xb3a333c6,0xaa7cad46,0x33d6b38e,0x33dcb1f8,0xaa013154,0xb3fe3318,0x20e8af64,0x3381b3f8,0x2d8d2597,
  0xb14f335c,0xb1fc2e48,0x2d3ab199,0x3390b1b8,0x29092c7b,0xb3e633ae,0xb03026f5,0x32d1b3f4,0x32e8b084,0xb00a329b,0xb3ed32b3,0x285bb05f,
  0x29cfb005,0x33deb2eb,0xb05a325c,0xb2b630db,0xafbd2922,0x3301b3e5,0x27272b59,0xb3f333c9,0xb36f3200,0x2debb14a,0x31bcaf0a,0xb194332f,
  0xb39f33ff,0xacdba084,0x33f9b347,0xa5652ea4,0x3394b2ba,0xad233055,0xa438a9b6,0x33fcb3df,0x33e4b3f9,0x293b2533,0xb03a2ce7,0x32cbb39e,
  0x3258b357,0x30e0ae5f,0xb2ee31c0,0x2ffeb190,0x2e99b0f8,0x334ab245,0xb3ff33b2,0x201fac63,0xaf4230a3,0xb3213285,0x3133b040,0xb21532c7,
  0xa99e2d17,0xb3e03396,0x32bdb209,0xb0503141,0x278b1f76,0xb3f233ff,0x33b3b34c,0xac572e8d,0x2e6bac32,0xb35433b8,0x3400b3ef,0x1d1b2810,
  0xb289324d,0x309eb0ee,0xb3ce33b5,0x2b0fac4b,0xb2f432c1,0x2fe8b04a,0xb3f033e1,0x27efa985,0xb34f3324,0x2e82af37,0xb3ff33fa,0x1eada4ce,
  0xb3983376,0x2d0badc8,0xb3fb33ff,0xa49c1de4,0x351c35f6,0xac93a617,0xb8a3b93c,0x308d2a16,0x32f43448,0xb160afa5,0xb6a4b7fe,0x353a3389,
  0x2fa53160,0xb448b2f4,0xb389b53a,0x37fe36a4,0x26172c93,0xb5f6b51c,0xaa16b08d,0x393c38a3,0x34c3358c,0xac47a5b2,0xb85fb8f3,0x304229b1,
  0x327e33fd,0xb106af26,0xb63cb785,0x34e7330f,0x2f263106,0xb3fdb27e,0xb30fb4e7,0x3785363c,0x25b22c47,0xb58cb4c3,0xa9b1b042,0x38f3385f,
  0x346a3523,0xabf6a54d,0xb81ab8a8,0x2fef294d,0x3209336b,0xb0acaea7,0xb5d4b70a,0x34933294,0x2ea730ac,0xb36bb209,0xb294b493,0x370a35d4,
  0x254d2bf6,0xb523b46a,0xa94dafef,0x38a8381a,0x341334bc,0xab5fa4e9,0xb7a6b85a,0x2f5928e8,0x319432da,0xb052ae28,0xb56ab68d,0x343e3219,
  0x2e283052,0xb2dab194,0xb219b43e,0x368d356a,0x24e92b5f,0xb4bcb413,0xa8e8af59,0x385a37a6,0x33783456,0xaac8a484,0xb715b80a,0x2ec32884,
  0x3120324a,0xaff2ada9,0xb4ffb60e,0x33d3319e,0x2da92ff2,0xb24ab120,0xb19eb3d3,0x360e34ff,0x24842ac8,0xb456b378,0xa884aec3,0x380a3715,
  0x32cd33e3,0xaa31a420,0xb682b76f,0x2e2d281f,0x30ac31bb,0xaf3fad2a,0xb493b58d,0x33283122,0x2d2a2f3f,0xb1bbb0ac,0xb122b328,0x358d3493,
  0x24202a31,0xb3e3b2cd,0xa81fae2d,0x376f3682,0x3223331c,0xa999a376,0xb5ebb6c6,0x2d972776,0x3039312d,0xae8dacac,0xb426b50b,0x327c30a6,
  0x2cac2e8d,0xb12db039,0xb0a6b27c,0x350b3426,0x23762999,0xb31cb223,0xa776ad97,0x36c635eb,0x317a3257,0xa902a2ad,0xb552b61a,0x2d0026ad,
  0x2f8c309f,0xaddcac2e,0xb371b487,0x31cf3029,0x2c2e2ddc,0xb09faf8c,0xb029b1cf,0x34873371,0x22ad2902,0xb257b17a,0xa6adad00,0x361a3552,
  0x30d23194,0xa86ba1e4,0xb4b7b56a,0x2c6a25e4,0x2ea73012,0xad2aab5f,0xb294b402,0x31222f59,0x2b5f2d2a,0xb012aea7,0xaf59b122,0x34023294,
  0x21e4286b,0xb194b0d2,0xa5e4ac6a,0x356a34b7,0x302c30d2,0xa7a9a11b,0xb41ab4b7,0x2ba7251b,0x2dc22f0c,0xac79aa63,0xb1b6b2f7,0x30742e5f,
  0x2a632c79,0xaf0cadc2,0xae5fb074,0x32f731b6,0x211b27a9,0xb0d2b02c,0xa51baba7,0x34b7341a,0x2f0c3012,0xa67ba052,0xb2f7b402,0x2a7a2452,
  0x2cde2df5,0xab91a967,0xb0d7b1e8,0x2f8b2d65,0x29672b91,0xadf5acde,0xad65af8b,0x31e830d7,0x2052267b,0xb012af0c,0xa452aa7a,0x340232f7,
  0x2dc22ea7,0xa54d9f12,0xb1b6b294,0x294d2311,0x2bf62cde,0xaa31a86b,0xafefb0d7,0x2e2d2c6a,0x286b2a31,0xacdeabf6,0xac6aae2d,0x30d72fef,
  0x1f12254d,0xaea7adc2,0xa311a94d,0x329431b6,0x2c792d2a,0xa4209d7f,0xb074b122,0x281f217f,0x2a312b91,0xa8d0a6e0,0xae2daf8b,0x2cce2ade,
  0x26e028d0,0xab91aa31,0xaadeacce,0x2f8b2e2d,0x1d7f2420,0xad2aac79,0xa17fa81f,0x31223074,0x2a632b5f,0xa1e49bdb,0xae5faf59,0x25e41fdb,
  0x286b2967,0xa6e0a4e9,0xac6aad65,0x2ade28e8,0x24e926e0,0xa967a86b,0xa8e8aade,0x2d652c6a,0x1bdb21e4,0xab5faa63,0x9fdba5e4,0x2f592e5f,
  0x27a9286b,0x9f1298b6,0xaba7ac6a,0x23111cb6,0x254d267b,0xa420a1e4,0xa94daa7a,0x281f25e4,0x21e42420,0xa67ba54d,0xa5e4a81f,0x2a7a294d,
  0x18b61f12,0xa86ba7a9,0x9cb6a311,0x2c6a2ba7,0x211b21e4,0x98b69248,0xa51ba5e4,0x1cb61648,0x1f122052,0x9d7f9bdb,0xa311a452,0x217f1fdb,
  0x1bdb1d7f,0xa0529f12,0x9fdba17f,0x24522311,0x124818b6,0xa1e4a11b,0x96489cb6,0x25e4251b,0xa11ba1e4,0x18b61248,0x251b25e4,0x9cb69648,
  0x9f12a052,0x1d7f1bdb,0x23112452,0xa17f9fdb,0x9bdb9d7f,0x20521f12,0x1fdb217f,0xa452a311,0x924898b6,0x21e4211b,0x16481cb6,0xa5e4a51b,
  0xa7a9a86b,0x1f1218b6,0x2ba72c6a,0xa3119cb6,0xa54da67b,0x242021e4,0x294d2a7a,0xa81fa5e4,0xa1e4a420,0x267b254d,0x25e4281f,0xaa7aa94d,
  0x98b69f12,0x286b27a9,0x1cb62311,0xac6aaba7,0xaa63ab5f,0x21e41bdb,0x2e5f2f59,0xa5e49fdb,0xa86ba967,0x26e024e9,0x2c6a2d65,0xaadea8e8,
  0xa4e9a6e0,0x2967286b,0x28e82ade,0xad65ac6a,0x9bdba1e4,0x2b5f2a63,0x1fdb25e4,0xaf59ae5f,0xac79ad2a,0x24201d7f,0x30743122,0xa81fa17f,
  0xaa31ab91,0x28d026e0,0x2e2d2f8b,0xacceaade,0xa6e0a8d0,0x2b912a31,0x2ade2cce,0xaf8bae2d,0x9d7fa420,0x2d2a2c79,0x217f281f,0xb122b074,
  0xadc2aea7,0x254d1f12,0x31b63294,0xa94da311,0xabf6acde,0x2a31286b,0x2fef30d7,0xae2dac6a,0xa86baa31,0x2cde2bf6,0x2c6a2e2d,0xb0d7afef,
  0x9f12a54d,0x2ea72dc2,0x2311294d,0xb294b1b6,0xaf0cb012,0x267b2052,0x32f73402,0xaa7aa452,0xacdeadf5,0x2b912967,0x30d731e8,0xaf8bad65,
  0xa967ab91,0x2df52cde,0x2d652f8b,0xb1e8b0d7,0xa052a67b,0x30122f0c,0x24522a7a,0xb402b2f7,0xb02cb0d2,0x27a9211b,0x341a34b7,0xaba7a51b,
  0xadc2af0c,0x2c792a63,0x31b632f7,0xb074ae5f,0xaa63ac79,0x2f0c2dc2,0x2e5f3074,0xb2f7b1b6,0xa11ba7a9,0x30d2302c,0x251b2ba7,0xb4b7b41a,
  0xb0d2b194,0x286b21e4,0x34b7356a,0xac6aa5e4,0xaea7b012,0x2d2a2b5f,0x32943402,0xb122af59,0xab5fad2a,0x30122ea7,0x2f593122,0xb402b294,
  0xa1e4a86b,0x319430d2,0x25e42c6a,0xb56ab4b7,0xb17ab257,0x290222ad,0x3552361a,0xad00a6ad,0xaf8cb09f,0x2ddc2c2e,0x33713487,0xb1cfb029,
  0xac2eaddc,0x309f2f8c,0x302931cf,0xb487b371,0xa2ada902,0x3257317a,0x26ad2d00,0xb61ab552,0xb223b31c,0x29992376,0x35eb36c6,0xad97a776,
  0xb039b12d,0x2e8d2cac,0x3426350b,0xb27cb0a6,0xacacae8d,0x312d3039,0x30a6327c,0xb50bb426,0xa376a999,0x331c3223,0x27762d97,0xb6c6b5eb,
  0xb2cdb3e3,0x2a312420,0x3682376f,0xae2da81f,0xb0acb1bb,0x2f3f2d2a,0x3493358d,0xb328b122,0xad2aaf3f,0x31bb30ac,0x31223328,0xb58db493,
  0xa420aa31,0x33e332cd,0x281f2e2d,0xb76fb682,0xb378b456,0x2ac82484,0x3715380a,0xaec3a884,0xb120b24a,0x2ff22da9,0x34ff360e,0xb3d3b19e,
  0xada9aff2,0x324a3120,0x319e33d3,0xb60eb4ff,0xa484aac8,0x34563378,0x28842ec3,0xb80ab715,0xb413b4bc,0x2b5f24e9,0x37a6385a,0xaf59a8e8,
  0xb194b2da,0x30522e28,0x356a368d,0xb43eb219,0xae28b052,0x32da3194,0x3219343e,0xb68db56a,0xa4e9ab5f,0x34bc3413,0x28e82f59,0xb85ab7a6,
  0xb46ab523,0x2bf6254d,0x381a38a8,0xafefa94d,0xb209b36b,0x30ac2ea7,0x35d4370a,0xb493b294,0xaea7b0ac,0x336b3209,0x32943493,0xb70ab5d4,
  0xa54dabf6,0x3523346a,0x294d2fef,0xb8a8b81a,0xb4c3b58c,0x2c4725b2,0x385f38f3,0xb042a9b1,0xb27eb3fd,0x31062f26,0x363c3785,0xb4e7b30f,
  0xaf26b106,0x33fd327e,0x330f34e7,0xb785b63c,0xa5b2ac47,0x358c34c3,0x29b13042,0xb8f3b85f,0xb51cb5f6,0x2c932617,0x38a3393c,0xb08daa16,
  0xb2f4b448,0x31602fa5,0x36a437fe,0xb53ab389,0xafa5b160,0x344832f4,0x3389353a,0xb7feb6a4,0xa617ac93,0x35f6351c,0x2a16308d,0xb93cb8a3,
};
__device__ __align__(128) const uint32_t c_img[2560] = {
  0x326d31ed,0x333b32dd,0x33c33388,0x33fe33ea,0x33c331ed,0x31ed33c3,0xa8b22d64,0xb33bb0c4,0x33ea31ed,0xad64301d,0xb2ddb388,0x315fa8b2,
  0x32dd31ed,0xb3feabc6,0x326dad64,0xad64326d,0x30c431ed,0xaed7b2dd,0x2bc63388,0xa248b3ea,0x2bc631ed,0x315fb3c3,0xb3ea2d64,0x2ed730c4,
  0xa8b231ed,0x3388b01d,0x301db388,0xb1ed28b2,0xb01d31ed,0x22482bc6,0x30c4ad64,0x3388b26d,0x33ea33fe,0x338833c3,0x32dd333b,0x31ed326d,
  0xb2ddb3fe,0xa248b01d,0x326d2ed7,0x338833ea,0x30c433fe,0xb33babc6,0xabc6b33b,0x33fe30c4,0xabc6b3fe,0x31ed32dd,0xb3eaaed7,0x333ba8b2,
  0xa8b233fe,0x2d64b3c3,0xb01d333b,0x315fb26d,0x301db3fe,0xb3fe301d,0x30c42ed7,0x2d64b3ea,0xb26d33fe,0x2ed72bc6,0x33c3b33b,0xa248b0c4,
  0x33c3b3fe,0x315fb2dd,0x28b2aed7,0xaed728b2,0xb0c4b15f,0xaed7b01d,0xabc6ad64,0xa248a8b2,0xabc6b15f,0x315f2bc6,0x33ea3388,0x2ed7326d,
  0x28b2b15f,0x338832dd,0xb01d2d64,0xb1edb3ea,0x301db15f,0x224833c3,0xb0c4b388,0x338830c4,0x326db15f,0xb33b301d,0x33c3ad64,0xb3fe28b2,
  0x33c3b15f,0xb1edabc6,0xa8b23388,0x333bb26d,0x33eab15f,0x2d64b2dd,0xb2dd2d64,0xb15f33ea,0x32ddb15f,0x33feb3c3,0x326db388,0x2d64b0c4,
  0x28b22248,0x2d642bc6,0x301d2ed7,0x315f30c4,0xb01da248,0xb3feb2dd,0xb0c4b33b,0x2d64a8b2,0x326d2248,0x2ed733c3,0xb3c3aed7,0xa248b26d,
  0xb3c3a248,0x315fb01d,0xa8b2333b,0xaed7b3ea,0x33ea2248,0xb388abc6,0x32dd2ed7,0xb1edb0c4,0xb2dda248,0x224832dd,0x326db33b,0xb38828b2,
  0x30c42248,0x333bb3c3,0xabc6aed7,0xb3fe326d,0xabc6a248,0xb1ed301d,0xb3ea333b,0xb33b33ea,0xb26d31ed,0xb33b32dd,0xb3c33388,0xb3fe33ea,
  0xb3c331ed,0xb1ed33c3,0x28b22d64,0x333bb0c4,0xb3ea31ed,0x2d64301d,0x32ddb388,0xb15fa8b2,0xb2dd31ed,0x33feabc6,0xb26dad64,0x2d64326d,
  0xb0c431ed,0x2ed7b2dd,0xabc63388,0x2248b3ea,0xabc631ed,0xb15fb3c3,0x33ea2d64,0xaed730c4,0x28b231ed,0xb388b01d,0xb01db388,0x31ed28b2,
  0x301d31ed,0xa2482bc6,0xb0c4ad64,0xb388b26d,0xb3ea33fe,0xb38833c3,0xb2dd333b,0xb1ed326d,0x32ddb3fe,0x2248b01d,0xb26d2ed7,0xb38833ea,
  0xb0c433fe,0x333babc6,0x2bc6b33b,0xb3fe30c4,0x2bc6b3fe,0xb1ed32dd,0x33eaaed7,0xb33ba8b2,0x28b233fe,0xad64b3c3,0x301d333b,0xb15fb26d,
  0xb01db3fe,0x33fe301d,0xb0c42ed7,0xad64b3ea,0x326d33fe,0xaed72bc6,0xb3c3b33b,0x2248b0c4,0xb3c3b3fe,0xb15fb2dd,0xa8b2aed7,0x2ed728b2,
  0x30c4b15f,0x2ed7b01d,0x2bc6ad64,0x2248a8b2,0x2bc6b15f,0xb15f2bc6,0xb3ea3388,0xaed7326d,0xa8b2b15f,0xb38832dd,0x301d2d64,0x31edb3ea,
  0xb01db15f,0xa24833c3,0x30c4b388,0xb38830c4,0xb26db15f,0x333b301d,0xb3c3ad64,0x33fe28b2,0xb3c3b15f,0x31edabc6,0x28b23388,0xb33bb26d,
  0xb3eab15f,0xad64b2dd,0x32dd2d64,0x315f33ea,0xb2ddb15f,0xb3feb3c3,0xb26db388,0xad64b0c4,0xa8b22248,0xad642bc6,0xb01d2ed7,0xb15f30c4,
  0x301da248,0x33feb2dd,0x30c4b33b,0xad64a8b2,0xb26d2248,0xaed733c3,0x33c3aed7,0x2248b26d,0x33c3a248,0xb15fb01d,0x28b2333b,0x2ed7b3ea,
  0xb3ea2248,0x3388abc6,0xb2dd2ed7,0x31edb0c4,0x32dda248,0xa24832dd,0xb26db33b,0x338828b2,0xb0c42248,0xb33bb3c3,0x2bc6aed7,0x33fe326d,
  0x2bc6a248,0x31ed301d,0x33ea333b,0x333b33ea,0x30c4315f,0x2ed7301d,0x2bc62d64,0x224828b2,0x2bc6315f,0xb15fabc6,0xb3eab388,0xaed7b26d,
  0xa8b2315f,0xb388b2dd,0x301dad64,0x31ed33ea,0xb01d315f,0xa248b3c3,0x30c43388,0xb388b0c4,0xb26d315f,0x333bb01d,0xb3c32d64,0x33fea8b2,
  0xb3c3315f,0x31ed2bc6,0x28b2b388,0xb33b326d,0xb3ea315f,0xad6432dd,0x32ddad64,0x315fb3ea,0xb2dd315f,0xb3fe33c3,0xb26d3388,0xad6430c4,
  0xa8b2a248,0xad64abc6,0xb01daed7,0xb15fb0c4,0x301d2248,0x33fe32dd,0x30c4333b,0xad6428b2,0xb26da248,0xaed7b3c3,0x33c32ed7,0x2248326d,
  0x33c32248,0xb15f301d,0x28b2b33b,0x2ed733ea,0xb3eaa248,0x33882bc6,0xb2ddaed7,0x31ed30c4,0x32dd2248,0xa248b2dd,0xb26d333b,0x3388a8b2,
  0xb0c4a248,0xb33b33c3,0x2bc62ed7,0x33feb26d,0x2bc62248,0x31edb01d,0x33eab33b,0x333bb3ea,0x326d31ed,0x333b32dd,0x33c33388,0x33fe33ea,
  0x33c331ed,0x31ed33c3,0xa8b22d64,0xb33bb0c4,0x33ea31ed,0xad64301d,0xb2ddb388,0x315fa8b2,0x32dd31ed,0xb3feabc6,0x326dad64,0xad64326d,
  0x30c431ed,0xaed7b2dd,0x2bc63388,0xa248b3ea,0x2bc631ed,0x315fb3c3,0xb3ea2d64,0x2ed730c4,0xa8b231ed,0x3388b01d,0x301db388,0xb1ed28b2,
  0xb01d31ed,0x22482bc6,0x30c4ad64,0x3388b26d,0x33ea33fe,0x338833c3,0x32dd333b,0x31ed326d,0xb2ddb3fe,0xa248b01d,0x326d2ed7,0x338833ea,
  0x30c433fe,0xb33babc6,0xabc6b33b,0x33fe30c4,0xabc6b3fe,0x31ed32dd,0xb3eaaed7,0x333ba8b2,0xa8b233fe,0x2d64b3c3,0xb01d333b,0x315fb26d,
  0x301db3fe,0xb3fe301d,0x30c42ed7,0x2d64b3ea,0xb26d33fe,0x2ed72bc6,0x33c3b33b,0xa248b0c4,0x33c3b3fe,0x315fb2dd,0x28b2aed7,0xaed728b2,
  0xb0c4315f,0xaed7301d,0xabc62d64,0xa24828b2,0xabc6315f,0x315fabc6,0x33eab388,0x2ed7b26d,0x28b2315f,0x3388b2dd,0xb01dad64,0xb1ed33ea,
  0x301d315f,0x2248b3c3,0xb0c43388,0x3388b0c4,0x326d315f,0xb33bb01d,0x33c32d64,0xb3fea8b2,0x33c3315f,0xb1ed2bc6,0xa8b2b388,0x333b326d,
  0x33ea315f,0x2d6432dd,0xb2ddad64,0xb15fb3ea,0x32dd315f,0x33fe33c3,0x326d3388,0x2d6430c4,0x28b2a248,0x2d64abc6,0x301daed7,0x315fb0c4,
  0xb01d2248,0xb3fe32dd,0xb0c4333b,0x2d6428b2,0x326da248,0x2ed7b3c3,0xb3c32ed7,0xa248326d,0xb3c32248,0x315f301d,0xa8b2b33b,0xaed733ea,
  0x33eaa248,0xb3882bc6,0x32ddaed7,0xb1ed30c4,0xb2dd2248,0x2248b2dd,0x326d333b,0xb388a8b2,0x30c4a248,0x333b33c3,0xabc62ed7,0xb3feb26d,
  0xabc62248,0xb1edb01d,0xb3eab33b,0xb33bb3ea,0xb26d31ed,0xb33b32dd,0xb3c33388,0xb3fe33ea,0xb3c331ed,0xb1ed33c3,0x28b22d64,0x333bb0c4,
  0xb3ea31ed,0x2d64301d,0x32ddb388,0xb15fa8b2,0xb2dd31ed,0x33feabc6,0xb26dad64,0x2d64326d,0xb0c431ed,0x2ed7b2dd,0xabc63388,0x2248b3ea,
  0xabc631ed,0xb15fb3c3,0x33ea2d64,0xaed730c4,0x28b231ed,0xb388b01d,0xb01db388,0x31ed28b2,0x301d31ed,0xa2482bc6,0xb0c4ad64,0xb388b26d,
  0xb3ea33fe,0xb38833c3,0xb2dd333b,0xb1ed326d,0x32ddb3fe,0x2248b01d,0xb26d2ed7,0xb38833ea,0xb0c433fe,0x333babc6,0x2bc6b33b,0xb3fe30c4,
  0x2bc6b3fe,0xb1ed32dd,0x33eaaed7,0xb33ba8b2,0x28b233fe,0xad64b3c3,0x301d333b,0xb15fb26d,0xb01db3fe,0x33fe301d,0xb0c42ed7,0xad64b3ea,
  0x326d33fe,0xaed72bc6,0xb3c3b33b,0x2248b0c4,0xb3c3b3fe,0xb15fb2dd,0xa8b2aed7,0x2ed728b2,0x29ed29ed,0x29ed29ed,0x29ed29ed,0x29ed29ed,
  0x2bc32a6d,0x2add2bea,0x23c628c4,0xa81da0b2,0x2bc32add,0xa3c6281d,0xabc3aadd,0x23c6a81d,0x29ed2b3b,0xabfea564,0x295fa6d7,0x1a482b88,
  0x25642b88,0xa564ab88,0x25642b88,0xa564ab88,0xa0b22bc3,0x2a6daadd,0xabea23c6,0x28c4281d,0xa8c42bea,0x2a6da0b2,0x28c4abea,0xaa6d20b2,
  0xab3b2bfe,0xa564295f,0x26d79a48,0x2b88a9ed,0x29ed29ed,0x29ed29ed,0x29ed29ed,0x29ed29ed,0xabc3aa6d,0xaaddabea,0xa3c6a8c4,0x281d20b2,
  0x2bc32add,0xa3c6281d,0xabc3aadd,0x23c6a81d,0xa9edab3b,0x2bfe2564,0xa95f26d7,0x9a48ab88,0x25642b88,0xa564ab88,0x25642b88,0xa564ab88,
  0x20b2abc3,0xaa6d2add,0x2beaa3c6,0xa8c4a81d,0xa8c42bea,0x2a6da0b2,0x28c4abea,0xaa6d20b2,0x2b3babfe,0x2564a95f,0xa6d71a48,0xab8829ed,
  0x295f295f,0x295f295f,0x295f295f,0x295f295f,0x23c628c4,0xa81da0b2,0xabc3aa6d,0xaaddabea,0xa3c6281d,0xabc3aadd,0x23c6a81d,0x2bc32add,
  0xa95f26d7,0x9a48ab88,0x29ed2b3b,0xabfea564,0xab882564,0x2b88a564,0xab882564,0x2b88a564,0xabea23c6,0x28c4281d,0x20b2abc3,0xaa6d2add,
  0xaa6d20b2,0xa8c42bea,0x2a6da0b2,0x28c4abea,0xa6d71a48,0xab8829ed,0xab3b2bfe,0xa564295f,0x295f295f,0x295f295f,0x295f295f,0x295f295f,
  0xa3c6a8c4,0x281d20b2,0x2bc32a6d,0x2add2bea,0xa3c6281d,0xabc3aadd,0x23c6a81d,0x2bc32add,0x295fa6d7,0x1a482b88,0xa9edab3b,0x2bfe2564,
  0xab882564,0x2b88a564,0xab882564,0x2b88a564,0x2beaa3c6,0xa8c4a81d,0xa0b22bc3,0x2a6daadd,0xaa6d20b2,0xa8c42bea,0x2a6da0b2,0x28c4abea,
  0x26d79a48,0x2b88a9ed,0x2b3babfe,0x2564a95f,0xabfe2bfe,0xabfe2bfe,0xabfe2bfe,0xabfe2bfe,0xaadd2bea,0xa3c628c4,0x281da0b2,0x2bc3aa6d,
  0xa81d2bc3,0x2adda3c6,0x281dabc3,0xaadd23c6,0x9a482b88,0x29edab3b,0xabfe2564,0x295f26d7,0x26d72b3b,0xa6d7ab3b,0x26d72b3b,0xa6d7ab3b,
  0x2a6d2add,0xabeaa3c6,0x28c4a81d,0x20b22bc3,0x2bea2a6d,0xa0b228c4,0xabeaaa6d,0x20b2a8c4,0x2b8829ed,0x2b3b2bfe,0x2564295f,0xa6d79a48,
  0xabfe2bfe,0xabfe2bfe,0xabfe2bfe,0xabfe2bfe,0x2addabea,0x23c6a8c4,0xa81d20b2,0xabc32a6d,0xa81d2bc3,0x2adda3c6,0x281dabc3,0xaadd23c6,
  0x1a48ab88,0xa9ed2b3b,0x2bfea564,0xa95fa6d7,0x26d72b3b,0xa6d7ab3b,0x26d72b3b,0xa6d7ab3b,0xaa6daadd,0x2bea23c6,0xa8c4281d,0xa0b2abc3,
  0x2bea2a6d,0xa0b228c4,0xabeaaa6d,0x20b2a8c4,0xab88a9ed,0xab3babfe,0xa564a95f,0x26d71a48,0x1a489a48,0x1a489a48,0x1a489a48,0x1a489a48,
  0x281da0b2,0x2bc3aa6d,0x2addabea,0x23c6a8c4,0x2adda3c6,0x281dabc3,0xaadd23c6,0xa81d2bc3,0x2bfea564,0xa95fa6d7,0x9a482b88,0x29edab3b,
  0x2b3ba6d7,0xab3b26d7,0x2b3ba6d7,0xab3b26d7,0x28c4a81d,0x20b22bc3,0xaa6daadd,0x2bea23c6,0x20b2a8c4,0x2bea2a6d,0xa0b228c4,0xabeaaa6d,
  0xa564a95f,0x26d71a48,0x2b8829ed,0x2b3b2bfe,0x1a489a48,0x1a489a48,0x1a489a48,0x1a489a48,0xa81d20b2,0xabc32a6d,0xaadd2bea,0xa3c628c4,
  0x2adda3c6,0x281dabc3,0xaadd23c6,0xa81d2bc3,0xabfe2564,0x295f26d7,0x1a48ab88,0xa9ed2b3b,0x2b3ba6d7,0xab3b26d7,0x2b3ba6d7,0xab3b26d7,
  0xa8c4281d,0xa0b2abc3,0x2a6d2add,0xabeaa3c6,0x20b2a8c4,0x2bea2a6d,0xa0b228c4,0xabeaaa6d,0x2564295f,0xa6d79a48,0xab88a9ed,0xab3babfe,
  0xa95fa95f,0xa95fa95f,0xa95fa95f,0xa95fa95f,0xa3c6a8c4,0x281d20b2,0x2bc32a6d,0x2add2bea,0x23c6a81d,0x2bc32add,0xa3c6281d,0xabc3aadd,
  0x295fa6d7,0x1a482b88,0xa9edab3b,0x2bfe2564,0x2b88a564,0xab882564,0x2b88a564,0xab882564,0x2beaa3c6,0xa8c4a81d,0xa0b22bc3,0x2a6daadd,
  0x2a6da0b2,0x28c4abea,0xaa6d20b2,0xa8c42bea,0x26d79a48,0x2b88a9ed,0x2b3babfe,0x2564a95f,0xa95fa95f,0xa95fa95f,0xa95fa95f,0xa95fa95f,
  0x23c628c4,0xa81da0b2,0xabc3aa6d,0xaaddabea,0x23c6a81d,0x2bc32add,0xa3c6281d,0xabc3aadd,0xa95f26d7,0x9a48ab88,0x29ed2b3b,0xabfea564,
  0x2b88a564,0xab882564,0x2b88a564,0xab882564,0xabea23c6,0x28c4281d,0x20b2abc3,0xaa6d2add,0x2a6da0b2,0x28c4abea,0xaa6d20b2,0xa8c42bea,
  0xa6d71a48,0xab8829ed,0xab3b2bfe,0xa564295f,0x29ed29ed,0x29ed29ed,0x29ed29ed,0x29ed29ed,0x2bc32a6d,0x2add2bea,0x23c628c4,0xa81da0b2,
  0x2bc32add,0xa3c6281d,0xabc3aadd,0x23c6a81d,0x29ed2b3b,0xabfea564,0x295fa6d7,0x1a482b88,0x25642b88,0xa564ab88,0x25642b88,0xa564ab88,
  0xa0b22bc3,0x2a6daadd,0xabea23c6,0x28c4281d,0xa8c42bea,0x2a6da0b2,0x28c4abea,0xaa6d20b2,0xab3b2bfe,0xa564295f,0x26d79a48,0x2b88a9ed,
  0x29ed29ed,0x29ed29ed,0x29ed29ed,0x29ed29ed,0xabc3aa6d,0xaaddabea,0xa3c6a8c4,0x281d20b2,0x2bc32add,0xa3c6281d,0xabc3aadd,0x23c6a81d,
  0xa9edab3b,0x2bfe2564,0xa95f26d7,0x9a48ab88,0x25642b88,0xa564ab88,0x25642b88,0xa564ab88,0x20b2abc3,0xaa6d2add,0x2beaa3c6,0xa8c4a81d,
  0xa8c42bea,0x2a6da0b2,0x28c4abea,0xaa6d20b2,0x2b3babfe,0x2564a95f,0xa6d71a48,0xab8829ed,0x9a481a48,0x9a481a48,0x9a481a48,0x9a481a48,
  0xa81d20b2,0xabc32a6d,0xaadd2bea,0xa3c628c4,0xaadd23c6,0xa81d2bc3,0x2adda3c6,0x281dabc3,0xabfe2564,0x295f26d7,0x1a48ab88,0xa9ed2b3b,
  0xab3b26d7,0x2b3ba6d7,0xab3b26d7,0x2b3ba6d7,0xa8c4281d,0xa0b2abc3,0x2a6d2add,0xabeaa3c6,0xa0b228c4,0xabeaaa6d,0x20b2a8c4,0x2bea2a6d,
  0x2564295f,0xa6d79a48,0xab88a9ed,0xab3babfe,0x9a481a48,0x9a481a48,0x9a481a48,0x9a481a48,0x281da0b2,0x2bc3aa6d,0x2addabea,0x23c6a8c4,
  0xaadd23c6,0xa81d2bc3,0x2adda3c6,0x281dabc3,0x2bfea564,0xa95fa6d7,0x9a482b88,0x29edab3b,0xab3b26d7,0x2b3ba6d7,0xab3b26d7,0x2b3ba6d7,
  0x28c4a81d,0x20b22bc3,0xaa6daadd,0x2bea23c6,0xa0b228c4,0xabeaaa6d,0x20b2a8c4,0x2bea2a6d,0xa564a95f,0x26d71a48,0x2b8829ed,0x2b3b2bfe,
  0xabfe2bfe,0xabfe2bfe,0xabfe2bfe,0xabfe2bfe,0xaadd2bea,0xa3c628c4,0x281da0b2,0x2bc3aa6d,0xa81d2bc3,0x2adda3c6,0x281dabc3,0xaadd23c6,
  0x9a482b88,0x29edab3b,0xabfe2564,0x295f26d7,0x26d72b3b,0xa6d7ab3b,0x26d72b3b,0xa6d7ab3b,0x2a6d2add,0xabeaa3c6,0x28c4a81d,0x20b22bc3,
  0x2bea2a6d,0xa0b228c4,0xabeaaa6d,0x20b2a8c4,0x2b8829ed,0x2b3b2bfe,0x2564295f,0xa6d79a48,0xabfe2bfe,0xabfe2bfe,0xabfe2bfe,0xabfe2bfe,
  0x2addabea,0x23c6a8c4,0xa81d20b2,0xabc32a6d,0xa81d2bc3,0x2adda3c6,0x281dabc3,0xaadd23c6,0x1a48ab88,0xa9ed2b3b,0x2bfea564,0xa95fa6d7,
  0x26d72b3b,0xa6d7ab3b,0x26d72b3b,0xa6d7ab3b,0xaa6daadd,0x2bea23c6,0xa8c4281d,0xa0b2abc3,0x2bea2a6d,0xa0b228c4,0xabeaaa6d,0x20b2a8c4,
  0xab88a9ed,0xab3babfe,0xa564a95f,0x26d71a48,0x3bfb3bff,0x3be53bf2,0x3bbf3bd4,0x3b873ba5,0x3bd03bfb,0x3b013b7c,0x399d3a60,0x378538bc,
  0x35173b52,0xbbc9b7c8,0xb074ba9b,0x3bfe391b,0x319e3b27,0xbbf3b979,0x363cb80a,0x3a2d3bc5,0xba093986,0x3a7eb8f8,0xbae5385f,0x3b3db77a,
  0xbabd393c,0x3bb0b699,0xbc00305b,0x3ba730d7,0xbb2a35c8,0xb8353bb2,0x3a64b1e8,0x3962bbf7,0xba90350b,0xba413bff,0x3602340e,0x3bf6bad8,
  0xac6aa5e4,0xb122af59,0xb402b294,0xb56ab4b7,0xb2deac9c,0xb7bdb5a5,0xb9b3b8d6,0xbb10ba73,0xbb96b676,0xb359bafe,0x3bec3884,0x2a163a29,
  0xbbe0b72c,0x2f27b9d6,0x3b5e3ae8,0xb91633a2,0xb941b9c9,0x38ad3a45,0xb80fbab3,0x36d23b13,0xb850ba0d,0x346f3b4a,0x1fdbbbed,0xb4ab3be8,
  0x3721bb76,0xbace3463,0xb8d13bdd,0x39ebadfb,0x3894bb98,0xb8fd281f,0xbb6a3bbd,0x2e2d3825,0x3b3f3b65,0x3ae83b16,0x3a813ab6,0x3a0d3a49,
  0x3263356a,0xad972b43,0xb5dfb359,0xb8eeb7f3,0xa9b139aa,0xbbedba25,0x3340b889,0x3b983afb,0xbaa2aa16,0xb4cfbb8e,0x3c0038ad,0xb44b38e5,
  0xbb853625,0x3bbdb4c3,0xbbe432ad,0x3bfbaf8b,0xbaacb6d2,0x39243954,0xb65fbace,0x2fbd3bb8,0xb9661648,0xba603bf8,0x383a31cf,0x3b27bbb3,
  0x3219b9eb,0xbb1836f4,0xb9903be5,0x37dd3010,0xb6c6b61a,0xb80ab76f,0xb8a8b85a,0xb93cb8f3,0xbbd7bb87,0xbbf8bbfd,0xbb71bbc9,0xba4dbaf1,
  0xbbfeb9a6,0x305bb91f,0x3bcb3a97,0xb50b37d2,0xb87abbfe,0x3ba13546,0x24523a7e,0xbbb5ba54,0xb576bb63,0x340e3ba3,0xb13bbbd3,0x2c9c3bf2,
  0x386abb3d,0xba2139f8,0x3b57b835,0xbbf13432,0x39e7bc00,0xb8d6adc9,0xbacb3bde,0x372c3457,0x3bdab962,0x3764bb35,0xb9c03122,0xbaf73bef,
  0x398b39cd,0x38fd3946,0x386538b2,0x37853815,0xba85b9c9,0xbb92bb1e,0xbbfebbdd,0xbbc2bbf5,0xb66b3682,0xbb01bb94,0x387fb371,0x3a2d3beb,
  0xbac7bb76,0x3a00ad33,0x36bb3bd4,0xbbeab79b,0xbc0026ad,0x3bf32c38,0xbbd6b109,0x3ba733eb,0x3153bbff,0xb70a3b9e,0x396bba9b,0xbade390c,
  0xb5d4b5bc,0xbbb03b2c,0x32013830,0x3bf6ba67,0x3bccbb52,0x2c06b92e,0xbb83385f,0xb8c73bab,0xb9c5b982,0xba41ba04,0xbab0ba7a,0xbb10bae1,
  0xb8a3b986,0xb52fb74e,0xa94db1e8,0x33d32e91,0xbb54bb4f,0x37bdb523,0x3a9e3bc8,0xb916308d,0x3840b5c8,0x394a3bf9,0xbb42b294,0xb0a6bb0a,
  0x251bbbff,0xaf273bfc,0x327cbbe6,0xb4ab3bc0,0x3be325e4,0xbb2fb4e7,0x39e33884,0xb81aba35,0x3b73bb78,0xb46fb715,0xbbdc3ad1,0x2e2d38cc,
  0x33283676,0x3bfcba19,0x3581bab3,0xba6b3493,0x363136dd,0x34cf3581,0x32c6341a,0x2fbd3153,0xbae1bb65,0xb970ba39,0xb715b889,0xb16cb4f3,
  0xb9a12a7a,0xb924bbfe,0x3a933042,0x37dd3bcc,0x308db9aa,0x3b453b07,0xb94632ad,0xb845bbfa,0xbb68b55e,0x3b1836bb,0xbabab805,0x3a4d38a3,
  0x3bc0b625,0xbbfe2ec3,0x3b9431cf,0xba89b742,0x9cb6b95d,0xbbf8396b,0xb1b63a5c,0x3bb5b840,0x38cc9648,0x3b81bbac,0xac38b85a,0xbbce3933,
  0xbb60bb3a,0xbba1bb83,0xbbd2bbbc,0xbbf1bbe3,0x3815361a,0x39df3907,0x3b2c3a97,0x3be23b9c,0xb9afbbfd,0x3a21294d,0x388e3bee,0xbaf7b328,
  0x3beb39a6,0xb6af37a6,0xba04bbd3,0x3ac42d00,0x360ebb89,0xb7643b42,0x3855baeb,0xb8ee3a85,0x33eb3b63,0x28e8bbf5,0xb5233bde,0x389ebb21,
  0x3c00b9f0,0x2d97b9e3,0xbbdf38db,0xb44b3ac7,0xba673c00,0x358d3487,0x3bfcbab6,0x330fba15,0x3b7a3bf1,0x394a3a93,0x33893764,0xb3d39cb6,
  0x3afb3be2,0x35eb3946,0xb4c328e8,0xbaa9b8cc,0x27763af7,0xbb2fbaba,0x3a76ad97,0x30a63b60,0xaf8b3ac4,0xb994bb94,0x3bf8358d,0xb8743815,
  0xbb4c38ee,0x3bfcb1b6,0xbad5b4cf,0x381a39af,0xbbb3389e,0x3b592c38,0xb76fb970,0xb24b3beb,0xb9d2344b,0xbb923bd2,0xb0f03924,0x3a6bb60e,
  0xb8f3330f,0xbc003b2c,0xb91f3b45,0x323233eb,0xb5b1afbd,0xba00b88e,0xbbc6bb18,0xbbc2bc00,0xb7d2b16c,0xbb6fba04,0xbba3bbfe,0xb86fba67,
  0xbbffb7dd,0x370ab855,0x38b73bf8,0xbbeab631,0xbbf2b845,0x39bcb523,0x2dc93b81,0xbaa5bae1,0xb68dba4d,0xac063bdf,0x382abba1,0xbade39a1,
  0xb457ba89,0xb6543bfc,0x3b16b9df,0xbbd8308d,0x397dbbb5,0xb52fb2c6,0xbbe73a21,0xb8c73b68,0x3a49bbce,0x2311b715,0xba2536af,0xbbd93bc0,
  0xb958b785,0xbb81ba9e,0xbbefbbf3,0xba89bb73,0xbbf7bbc2,0xb9b8bb42,0xaf59b70a,0x384a3328,0xbb8bba2d,0x39dfb27c,0x34263bb0,0xbbceb98b,
  0xb4b7bbea,0x3b6c39e3,0xbafe2c06,0x3185ba85,0xaadebba7,0xb6af3bdc,0x3a58ba41,0xbbe2366b,0x3a29bade,0xbc003581,0x3a45352f,0xb2f7bac7,
  0x3b37bbf6,0x28e8b865,0xbaee37bd,0xbac43c00,0x3b13b8c7,0x3b5cbbfe,0x3463b94a,0xb8993153,0xb9f4bb10,0xb58db87f,0x3029af27,0x389e35d4,
  0x2dfbb3d3,0x399936bb,0x3bf23b2f,0x3ac13bcc,0x3552b916,0x39703bd6,0xbbbab46f,0x330fb9c5,0x3ba530a6,0xb5f7396b,0xb7c8bbfc,0x3be138a3,
  0x3bfdb4ab,0xbb45b201,0x38e038fd,0xb16cbb54,0x391b381a,0xa17fbb83,0xb8f83b92,0x3bcfb840,0x36e82e2d,0x3bfebab0,0x37febb01,0xb845251b,
  0xb77a3a6b,0x3648294d,0x3bb2ba00,0x3a8cbbe3,0xb742b93c,0x2311b340,0x37a6340e,0x3aa93966,0x3b963a4d,0x3b7f3c00,0x380f3a21,0xb0be3219,
  0x3933b50b,0x35eb3be4,0xbbf5b8d6,0x3874b6c6,0x39413bb5,0xbbffb65f,0x38d1b764,0x33ba3bd7,0x3b9c2c9c,0xb994b83a,0x34873ae8,0x324bbbfe,
  0xb7213bf1,0x3b47b990,0xbbbf2d97,0x38c1387a,0x2d00372c,0x3b59b8a8,0x3a39bbed,0xb232b576,0xbbfb3af7,0xb9743b71,0x307434cf,0x3adbb86a,
  0x3b213a0d,0x3c003bcb,0x3b073bbd,0x386f39e7,0x351738ee,0xb599a452,0xbae5b924,0xbbe9bbda,0x3a153b98,0xbb6fb13b,0x2ec3ba60,0x3aa53b3f,
  0xba09344b,0xa884bb57,0x3a643b18,0xbbc3b263,0xb4f33bfb,0x39bcbacb,0xbbac380a,0x3bd8a9b1,0xbb2aafbd,0x36a439c0,0x3402bbf8,0xba6f3aa2,
  0xbbfa3b27,0xb6543a81,0x3907b05b,0x3bd9bb85,0x2c6ab7dd,0xb9da35df,0xbbec3ba1,0xb8203aac,0x3bf53b87,0x3b6c3bec,0x392e3a7e,0x32f73721,
  0xb9e7b785,0xbbfcbb5e,0xba81bbb0,0xb43eb894,0x379b3bfe,0xbc00b80f,0x374eb835,0x38993bfb,0xbb3fba2d,0x3b329fdb,0xb3403a41,0xb8eabbd0,
  0xb90c3b3d,0x3b5cb8d1,0xbbf93122,0x3ac13517,0x29b1bba7,0xb94f3b6a,0x3be4b7bd,0xbaf4b19e,0xbbab3962,0xb9993bbf,0x34e73359,0x3be1ba09,
  0x3b85bbf6,0x353ab99d,0xb83a2f27,0xbbf03abd,0x2e91356a,0xb5f7b074,0xba19b8ad,0xbbcfbb2a,0xb966bb10,0xaba7b63c,0x38a8346f,0x3bb73a90,
  0xbb0aaa16,0xa17fbae5,0x3b1e3ace,0xba8c2c6a,0x36c6b916,0x36ff3c00,0xbbcbb8fd,0x3a50b2de,0xba35b6d2,0x36483a64,0x2d33bbe5,0xb84a3b96,
  0x3bfeb4ab,0xb9fcb602,0x313b3b01,0x37e8bbe0,0x3493b9eb,0xb9b83402,0xbb9e3bc9,0xb1853941,0x35762e2d,0x3b90b9b3,0x3acbbbf3,0x2fefb850,
  0x3a543bcf,0x2884374e,0xb9f8b648,0xbbe9bbab,0x398b3bb7,0xb4db3340,0xbbdcb9fc,0xb911bb85,0xb4323a8c,0xb6a4bbf9,0x3b3539b8,0xbbc3ae91,
  0xb66b3a50,0xad65bbe4,0x38653b90,0xbb0db966,0xbbef384a,0x39da34e7,0x2b43bb6c,0xba6f3b0a,0xbc0037e8,0x3759383a,0x387fbbfc,0xbbf636c6,
  0xb7f33185,0xbb7f3a19,0xbb8e3c00,0xb8203a35,0xb5d42fef,0xba1d38a8,0xbbd63b32,0xbba93bfe,0xb8e5b2f7,0xbbffbb1e,0xb954bb5c,0x30beb493,
  0xb9c5b43e,0xbb9fbbcb,0xb201b94f,0x3a313576,0xbbb8b899,0x3b47ad33,0xb6f43999,0xb3babbf5,0xbb54b8ea,0x3bf9313b,0xbab0353a,0x3790b9e7,
  0xb010bac1,0xb9743b9e,0x3bfdb5f7,0xb8c1b79b,0x251bbaf4,0xbb1b3acb,0x3a9e2ba7,0x2e5fbb3f,0x3af1bbe1,0x3599b92e,0xb546a17f,0xbadb390c,
  0x3b73bbf0,0x3929ba81,0x327cb6ff,0xb49f29b1,0xb825baa9,0x353aaec3,0x3b7c3994,0x3af43bfa,0x360eb0be,0x3bf43a64,0x388e3b47,0xb7372c6a,
  0x38bcb874,0x2ba73bac,0xb979bb59,0x3bf03742,0x3c0033ba,0xbb043402,0x3855b974,0xacce3b96,0x3bc5b24b,0xb6ffb907,0xb6993c00,0x3bb7b933,
  0x363138c1,0x3902bbec,0xbbdf3599,0x34ff3941,0x30d73232,0x39fcb7a6,0x3bffbb6f,0x3a50bb9c,0xb9a13adb,0xb47b380f,0x32c62884,0x3937b721,
  0x3ad8386f,0x3b903bf5,0x35a539bc,0xb7e8ad00,0x3b683be9,0x2ef538d1,0xba93b6a4,0xbb24bbfb,0x3a733aa5,0xbbfcb487,0x39d6b654,0xafef3b21,
  0x1cb63bc3,0xb7b2bbbf,0x3aba39da,0xbbfab517,0xb3a23bd8,0x3b32ba39,0xbb4a2311,0x343e3a15,0xbb603a6f,0x3a3d3074,0x31b6bb7f,0xbb9a3a09,
  0xbbe83bd9,0xb94f3b07,0xa81f35eb,0x38eab4f3,0xb9af3820,0xbbae3ae5,0xbbd23bff,0xba113b2a,0x319e389e,0xb929b426,0xbc00bb45,0xb911bb37,
  0xbbffbac1,0xb805bafe,0x382a217f,0x3bfd3b13,0xbabd330f,0x34dbba58,0x36023bfe,0xbb0db9f4,0xb68dbbe1,0x3a5c3a45,0xbbe7b648,0x3b89adfb,
  0xba90b16c,0x2d653aee,0x39b3bb81,0xbbf63552,0x397dbbcf,0xbbbc3463,0x338939b8,0x39f0bba5,0x32deb845,0xb7593029,0xbb5e39df,0xbba93bfd,
  0x3b7aba8c,0x3beebbf2,0x3a76bb6c,0x36ddb91b,0xbbe0ba89,0xba1dbbba,0x1fdbb6af,0x3a3136e8,0xa776b84a,0x3aeb37c8,0x3ad53c00,0xaa7a377a,
  0xb850bbce,0x3b9f38e0,0xbb6a28e8,0x3790b958,0x3b4cb185,0xb8db38f8,0x30f0bb5c,0x355e3bf7,0x3894bbe2,0xbbf937fe,0x399d358d,0x2e5fbb8b,
  0x39d232f7,0x341abbb2,0xbbc63999,0x395d34b7,0x3bd0bac4,0x3b1bbbef,0x363cb970,0xb49faade,0xb5b13899,0x30422f59,0x38b7b5f7,0x3b3aba29,
  0x3219b3d3,0x3b0438b7,0x3b713bfc,0x34ff397d,0x36e83aa9,0xb8b2adc9,0xbbefbb59,0xb5bcba49,0x3bd730a6,0xb902382a,0xa452bb92,0x39373b7a,
  0xb9583874,0x3371bb16,0x34263c00,0xb982bafb,0x387a381a,0x347bbbe7,0xbb573a00,0x3b242776,0xbb8b324b,0x31093a25,0x3a58bb6f,0xbb4f2f8b,
  0xb86a3a6b,0x2ef53389,0x39c0b70a,0x3bfabb4c,0xaadeb232,0xb83034c3,0xbaee39bc,0xbbff3bb3,0x3bda3bc2,0x37b23a76,0xb5df2c06,0xbb9ab9d2,
  0xbb37b86f,0xba7abbf8,0x3029b654,0x3b7838f3,0x32633bea,0xba3dbad5,0x3c00352f,0xba1135b1,0xb9f4baa5,0x3bc8376f,0xbbba2311,0x39cdb7d2,
  0xbaa23ade,0x3baeb0f0,0xb65fb94a,0xb7373bff,0x3552bbd8,0xbbe6391f,0x38e035eb,0x3682bbf2,0xbaac38c7,0xbbf43bc6,0xb9903b2f,0xacce368d,
  0x3bfdbbd9,0x3ad1bba3,0x37feb994,0x26adb457,0x38a33b9a,0xb8dba452,0xbb83bbae,0x2a7ab86a,0x37423b78,0xbab6b426,0xb907bbe6,0x39aa2ade,
  0xb8403a11,0x341abb57,0x294d3bf4,0xb55ebbda,0xb93339cd,0x3889ba58,0xb7a63ad1,0x3625bb37,0xbbe33737,0x304239c0,0x3b42bb04,0xb95db263,
  0xbb9c3682,0xb2ad3aee,0x3bf5b8b2,0x1648b9f4,0xb3282cce,0xb80535df,0xb9e33902,0xbb3a3aa2,0xad0026ad,0xb1cf3029,0xb4873371,0xb61a3552,
  0xba85b4ff,0xba5cbc00,0x3581b47b,0x3bfd3aac,0xbb21b5bc,0xb85abbba,0x3a393109,0x39a63bfd,0xbac7b937,0x3bbc365f,0xbbfeaef5,0x3b89b219,
  0xba15b982,0x3a9738e0,0xbb07b830,0x3b6336e8,0x3153bb24,0xbbee3990,0x36bb37b2,0x39f0bbd7,0x34f3bb4f,0xbbd337fe,0xaec33a7a,0x3c00b958,
  0x3bccbbfa,0x3aebbb71,0x396bba3d,0x36ddb87a,0x3bfabbff,0x3bdebbef,0x3bacbbc8,0x3b65bb8b,0x3bc03911,0x38303b6a,0xb946ad65,0xbb4fbbd0,
  0x3a353bfd,0xb85f30f0,0xbb1ebbbc,0x35c8b5b1,0x38cc3b0d,0xba7ab99d,0x3b943759,0xbbffb19e,0xb4933b89,0x31e8bbc6,0xad333bee,0xa5e4bbff,
  0xb8153bf6,0x3bc8b63c,0xac38ba1d,0xbb783abd,0xbbf539f0,0x329438b7,0x3b9ebaeb,0xb676b68d,0xbbeb3ba9,0xbbe63c00,0xbb2c3b9f,0xb9cd3a90,
  0xb79b36dd,0xb884382a,0xb92e38db,0xb9c9397d,0x33eb3a31,0xbad1b602,0xba04bbf9,0x3682b2de,0xb90c2a7a,0xbab3bbe7,0x374eb41a,0x3b763b7a,
  0xba673790,0x38b2b9b3,0xb5233b1b,0x26adbbe0,0xbbabb55e,0x3bdd3389,0xbbf9b042,0x3bff2776,0xbae12e5f,0xb3713b5e,0x3bfcb929,0xb5bcb850,
  0xae91b95d,0xbbd43a76,0x34e73805,0x3b52bb4c,0x308db49f,0xb1091fdb,0xb71534db,0xb9823894,0x3b0abb3a,0x3a9bbad5,0x3a19ba5c,0x3986b9d2,
  0x2f8bb7e8,0x3bde3979,0x376f3b32,0xb9aab0d7,0x3bb83b24,0xb1223855,0xbbfdba3d,0xaa16b9a1,0x3bb3afef,0xbab63699,0x391fb94f,0xb6253ad8,
  0x30103bfa,0xb359bbdf,0x35463bae,0xb6d2bb68,0x38f3343e,0x3889bbff,0xbba3353a,0x96483a73,0xbaf13b9a,0x38ad32c6,0x39f8bbf4,0xb9eb9cb6,
  0xb7d238ea,0xb2ad35a5,0x2dc92ba7,0x361ab3a2,0xba543a11,0xbace3a93,0xbb353b04,0xbb873b60,0x3bf23af4,0x31cf39d6,0xbb16b6ff,0xb9a6bbe8,
  0xb4323737,0xbbe5baba,0x2b43b902,0x3bfe39af,0x34573bf0,0xb85abb4a,0x3a2539fc,0xbb63b825,0xbbef2cce,0x3bc9b1b6,0xbb8e347b,0x3b3db60e,
  0xba493bb7,0x3a97a81f,0x34c3bb90,0xbc0038bc,0xb7f3b4ff,0xba7e3bd2,0x39542ef5,0x3962bc00,0xbafb3a50,0xbbd33b7c,0xbbf83bfc,0xbb653bc5,
  0x38e5b937,0x3835b88e,0x36f4b7b2,0x356ab631,0xbb13bbe9,0x31e8b6f4,0x3bf239da,0x36763af1,0x3be83911,0x340e3ab0,0xbb7cb759,0xb72cbb73,
  0x2dfbbbc3,0x32943bfd,0xb7c8bb7f,0x39c93a54,0x38253b0d,0xb8d6ba9e,0x39793a1d,0xba0db98b,0x3ba5ba6f,0xb884b546,0xb8f83bff,0x3b76b432,
  0xb8bc3bf6,0x3ae8b27c,0x3699bb9f,0xbb98366b,0x391bb820,0x3ab3b9f8,0x3bb2bb47,0x3bffbbef,0xbbc53ba9,0xbbed3bdc,0xbbff3bf9,0xbbfb3c00,
  0x377ab0be,0x3bdd3b35,0x2f593974,0xbb52b7f3,0x30d73a31,0xbbbdb865,0xb5a5bb1b,0x3b2735d4,0x3bf733ba,0xbbd42b43,0x3afeb599,0xb98638e5,
  0xbad83790,0x3a60b87f,0xb9d63929,0x393cb9c5,0x34b738c1,0x3a9bbb8e,0xba45a884,0xb5c83bb8,0xba732e5f,0xb80a3bd6,0x3b4ab4db,0x350bbb54,
  0xba293adb,0xb85f3954,0xb46336a4,0x25e43010,0x33a2b49f,0x305bb201,0x281fad65,0xac9c251b,0x3f803f80,0x3f803f80,0x3f803f80,0x3f803f80,
  0x3f803f80,0x3f803f80,0x3f803f80,0x3f803f80,0x3f803f80,0x3f803f80,0x3f803f80,0x3f803f80,0x3f803f80,0x3f803f80,0x3f803f80,0x3f803f80,
  0x3f803f80,0x3f803f80,0x3f803f80,0x3f803f80,0x3f803f80,0x3f803f80,0x3f803f80,0x3f803f80,0x3f803f80,0x3f803f80,0x3f803f80,0x3f803f80,
  0x3f803f80,0x3f803f80,0x3f803f80,0x3f803f80,0x3f803f80,0x3f803f80,0x3f803f80,0x3f803f80,0x3f803f80,0x3f803f80,0x3f803f80,0x3f803f80,
  0x3f803f80,0x3f803f80,0x3f803f80,0x3f803f80,0x3f803f80,0x3f803f80,0x3f803f80,0x3f803f80,0x3f803f80,0x3f803f80,0x3f803f80,0x3f803f80,
  0x3f803f80,0x3f803f80,0x3f803f80,0x3f803f80,0x3f803f80,0x3f803f80,0x3f803f80,0x3f803f80,0x3f803f80,0x3f803f80,0x3f803f80,0x3f803f80,
  0x3f803f80,0x3f803f80,0x3f803f80,0x3f803f80,0x3f803f80,0x3f803f80,0x3f803f80,0x3f803f80,0x3f803f80,0x3f803f80,0x3f803f80,0x3f803f80,
  0x3f803f80,0x3f803f80,0x3f803f80,0x3f803f80,0x3f803f80,0x3f803f80,0x3f803f80,0x3f803f80,0x3f803f80,0x3f803f80,0x3f803f80,0x3f803f80,
  0x3f803f80,0x3f803f80,0x3f803f80,0x3f803f80,0x3f803f80,0x3f803f80,0x3f803f80,0x3f803f80,0x3f803f80,0x3f803f80,0x3f803f80,0x3f803f80,
  0x3f803f80,0x3f803f80,0x3f803f80,0x3f803f80,0x3f803f80,0x3f803f80,0x3f803f80,0x3f803f80,0x3f803f80,0x3f803f80,0x3f803f80,0x3f803f80,
  0x3f803f80,0x3f803f80,0x3f803f80,0x3f803f80,0x3f803f80,0x3f803f80,0x3f803f80,0x3f803f80,0x3f803f80,0x3f803f80,0x3f803f80,0x3f803f80,
  0x3f803f80,0x3f803f80,0x3f803f80,0x3f803f80,0x3f803f80,0x3f803f80,0x3f803f80,0x3f803f80,0x3f803f80,0x3f803f80,0x3f803f80,0x3f803f80,
  0x3f803f80,0x3f803f80,0x3f803f80,0x3f803f80,0x3f803f80,0x3f803f80,0x3f803f80,0x3f803f80,0x3f803f80,0x3f803f80,0x3f803f80,0x3f803f80,
  0x3f803f80,0x3f803f80,0x3f803f80,0x3f803f80,0x3f803f80,0x3f803f80,0x3f803f80,0x3f803f80,0x3f803f80,0x3f803f80,0x3f803f80,0x3f803f80,
  0x3f803f80,0x3f803f80,0x3f803f80,0x3f803f80,0x3f803f80,0x3f803f80,0x3f803f80,0x3f803f80,0x3f803f80,0x3f803f80,0x3f803f80,0x3f803f80,
  0x3f803f80,0x3f803f80,0x3f803f80,0x3f803f80,0x3f803f80,0x3f803f80,0x3f803f80,0x3f803f80,0x3f803f80,0x3f803f80,0x3f803f80,0x3f803f80,
  0x3f803f80,0x3f803f80,0x3f803f80,0x3f803f80,0x3f803f80,0x3f803f80,0x3f803f80,0x3f803f80,0x3f803f80,0x3f803f80,0x3f803f80,0x3f803f80,
  0x3f803f80,0x3f803f80,0x3f803f80,0x3f803f80,0x3f803f80,0x3f803f80,0x3f803f80,0x3f803f80,0x3f803f80,0x3f803f80,0x3f803f80,0x3f803f80,
  0x3f803f80,0x3f803f80,0x3f803f80,0x3f803f80,0x3f803f80,0x3f803f80,0x3f803f80,0x3f803f80,0x3f803f80,0x3f803f80,0x3f803f80,0x3f803f80,
  0x3f803f80,0x3f803f80,0x3f803f80,0x3f803f80,0x3f803f80,0x3f803f80,0x3f803f80,0x3f803f80,0x3f803f80,0x3f803f80,0x3f803f80,0x3f803f80,
  0x3f803f80,0x3f803f80,0x3f803f80,0x3f803f80,0x3f803f80,0x3f803f80,0x3f803f80,0x3f803f80,0x3f803f80,0x3f803f80,0x3f803f80,0x3f803f80,
  0x3f803f80,0x3f803f80,0x3f803f80,0x3f803f80,0x3f803f80,0x3f803f80,0x3f803f80,0x3f803f80,0x3f803f80,0x3f803f80,0x3f803f80,0x3f803f80,
  0x3f803f80,0x3f803f80,0x3f803f80,0x3f803f80,0x3f803f80,0x3f803f80,0x3f803f80,0x3f803f80,0x3f803f80,0x3f803f80,0x3f803f80,0x3f803f80,
  0x3f803f80,0x3f803f80,0x3f803f80,0x3f803f80,0x3f803f80,0x3f803f80,0x3f803f80,0x3f803f80,0x3f803f80,0x3f803f80,0x3f803f80,0x3f803f80,
  0x3f803f80,0x3f803f80,0x3f803f80,0x3f803f80,0x3f803f80,0x3f803f80,0x3f803f80,0x3f803f80,0x3f803f80,0x3f803f80,0x3f803f80,0x3f803f80,
  0x3f803f80,0x3f803f80,0x3f803f80,0x3f803f80,0x3f803f80,0x3f803f80,0x3f803f80,0x3f803f80,0x3f803f80,0x3f803f80,0x3f803f80,0x3f803f80,
  0x3f803f80,0x3f803f80,0x3f803f80,0x3f803f80,0x3f803f80,0x3f803f80,0x3f803f80,0x3f803f80,0x3f803f80,0x3f803f80,0x3f803f80,0x3f803f80,
  0x3f803f80,0x3f803f80,0x3f803f80,0x3f803f80,0x3f803f80,0x3f803f80,0x3f803f80,0x3f803f80,0x3f803f80,0x3f803f80,0x3f803f80,0x3f803f80,
  0x3f803f80,0x3f803f80,0x3f803f80,0x3f803f80,0x3f803f80,0x3f803f80,0x3f803f80,0x3f803f80,0x3f803f80,0x3f803f80,0x3f803f80,0x3f803f80,
  0x3f803f80,0x3f803f80,0x3f803f80,0x3f803f80,0x3f803f80,0x3f803f80,0x3f803f80,0x3f803f80,0x3f803f80,0x3f803f80,0x3f803f80,0x3f803f80,
  0x3f803f80,0x3f803f80,0x3f803f80,0x3f803f80,0x3f803f80,0x3f803f80,0x3f803f80,0x3f803f80,0x3f803f80,0x3f803f80,0x3f803f80,0x3f803f80,
  0x3f803f80,0x3f803f80,0x3f803f80,0x3f803f80,0x3f803f80,0x3f803f80,0x3f803f80,0x3f803f80,0x3f803f80,0x3f803f80,0x3f803f80,0x3f803f80,
  0x3f803f80,0x3f803f80,0x3f803f80,0x3f803f80,0x3f803f80,0x3f803f80,0x3f803f80,0x3f803f80,0x3f803f80,0x3f803f80,0x3f803f80,0x3f803f80,
  0x3f803f80,0x3f803f80,0x3f803f80,0x3f803f80,0x3f803f80,0x3f803f80,0x3f803f80,0x3f803f80,0x3f803f80,0x3f803f80,0x3f803f80,0x3f803f80,
  0x3f803f80,0x3f803f80,0x3f803f80,0x3f803f80,0x3f803f80,0x3f803f80,0x3f803f80,0x3f803f80,0x3f803f80,0x3f803f80,0x3f803f80,0x3f803f80,
  0x3f803f80,0x3f803f80,0x3f803f80,0x3f803f80,0x3f803f80,0x3f803f80,0x3f803f80,0x3f803f80,0x3f803f80,0x3f803f80,0x3f803f80,0x3f803f80,
  0x3f803f80,0x3f803f80,0x3f803f80,0x3f803f80,0x3f803f80,0x3f803f80,0x3f803f80,0x3f803f80,0x3f803f80,0x3f803f80,0x3f803f80,0x3f803f80,
  0x3f803f80,0x3f803f80,0x3f803f80,0x3f803f80,0x3f803f80,0x3f803f80,0x3f803f80,0x3f803f80,0x3f803f80,0x3f803f80,0x3f803f80,0x3f803f80,
  0x3f803f80,0x3f803f80,0x3f803f80,0x3f803f80,0x3f803f80,0x3f803f80,0x3f803f80,0x3f803f80,0x3f803f80,0x3f803f80,0x3f803f80,0x3f803f80,
  0x3f803f80,0x3f803f80,0x3f803f80,0x3f803f80,0x3f803f80,0x3f803f80,0x3f803f80,0x3f803f80,0x3f803f80,0x3f803f80,0x3f803f80,0x3f803f80,
  0x3f803f80,0x3f803f80,0x3f803f80,0x3f803f80,0x3f803f80,0x3f803f80,0x3f803f80,0x3f803f80,0x3f803f80,0x3f803f80,0x3f803f80,0x3f803f80,
  0x3f803f80,0x3f803f80,0x3f803f80,0x3f803f80,0x3f803f80,0x3f803f80,0x3f803f80,0x3f803f80,0x3f803f80,0x3f803f80,0x3f803f80,0x3f803f80,
  0x3f803f80,0x3f803f80,0x3f803f80,0x3f803f80,0x3f803f80,0x3f803f80,0x3f803f80,0x3f803f80,0x3f803f80,0x3f803f80,0x3f803f80,0x3f803f80,
  0x3f803f80,0x3f803f80,0x3f803f80,0x3f803f80,
};

__device__ __align__(128) float    g_part[16][8][2176];
__device__ __align__(128) float    g_kv[16][2176];
__device__ __align__(128) uint4    g_o[16 * 16 * 1024];
__device__ __align__(128) unsigned g_ocnt[16 * 32];
__device__ unsigned g_epoch[128];
#define GSTAMP(role, i) do {} while (0)
#define STAMP(role, i) do {} while (0)

constexpr int STAGE_BYTES = 57344;
constexpr int OFF_PK = 0, OFF_V = 114688, OFF_H = 4 * 16384, OFF_VP = 9 * 16384;
constexpr int OFF_XT = 172032, XT_STRIDE = 4112;
constexpr int OFF_BAR = 204928, OFF_EPOCH = OFF_BAR + 640, OFF_EX = OFF_BAR + 672, OFF_SCALE = OFF_BAR + 704;
constexpr int OFF_F2F = 205824, OFF_F2I = 207872, OFF_F4 = 209920, OFF_ONES = 214016, OFF_KVB = 214016;
constexpr int OFF_STG = 219136, STG_STRIDE = 4352, SMEM_TOTAL = 232192;
enum { B_FULL1 = 0, B_EMPTY1 = 3, B_H = 6, B_HG = 8, B_XRAW = 10, B_XT = 11, B_KV = 12, B_Y = 13, B_PKFREE = 14, B_AFREE = 15,
       B_STG = 18, B_ODONE = 24, B_XFREE = 25, B_FULL2 = 33, B_CONS2 = 49, B_COUNT = 62 };
__host__ __device__ constexpr int bar_count(int i) {
  return i < B_EMPTY1 ? 1 : i < B_H ? 4 : i == B_XT ? 1 : i == B_KV ? 2 : i == B_PKFREE ? 4
       : (i >= B_AFREE && i < B_STG) ? 16 : i == B_ODONE ? 8 : (i >= B_XFREE && i < B_FULL2) ? 4
       : (i >= B_CONS2 && i <= B_CONS2 + 10) ? 4 : i >= B_CONS2 ? 2 : (i >= B_FULL2 && i < B_FULL2 + 7) ? 2 : 1;
}
__host__ __device__ constexpr uint64_t bar_counts(int r) {
  uint64_t v = 0;
  for (int w = 0; w < 12; w++) v |= (uint64_t)(bar_count(12 * r + w) - 1) << (4 * w);
  return v;
}
constexpr uint64_t SLOT_A = 0x9645296452964594ull;
constexpr uint64_t SLOT_B = 0x7103871038710326ull;
constexpr int SPIN_LIMIT = 1 << 22;
#define PKV CU_TENSOR_MAP_L2_PROMOTION_L2_128B
#define BPRE B_KV
#define PFD 3
#define PD1 500
#define PD2 300
#define HDELAY 1000
#define OC 1

__device__ __forceinline__ uint32_t smem_u32(const void* p) { return (uint32_t)__cvta_generic_to_shared(p); }
__device__ __forceinline__ void wg_fence() { asm volatile("wgmma.fence.sync.aligned;" ::: "memory"); }
__device__ __forceinline__ void wg_commit() { asm volatile("wgmma.commit_group.sync.aligned;" ::: "memory"); }
template <int N> __device__ __forceinline__ void wg_wait() { asm volatile("wgmma.wait_group.sync.aligned %0;" ::"n"(N) : "memory"); }
template <int N> __device__ __forceinline__ void keep(float (&d)[N]) {
#pragma unroll
  for (int i = 0; i < N; i++) asm volatile("" : "+f"(d[i])::"memory");
}
__device__ __forceinline__ uint64_t mkdesc(uint32_t addr, uint32_t lbo, uint32_t sbo, uint32_t swz) {
  uint32_t lo = ((addr & 0x3FFFF) >> 4) | ((lbo >> 4) << 16), hi = (sbo >> 4) | (swz << 30);
  return ((uint64_t)hi << 32) | lo;
}
__device__ __forceinline__ void mbar_init(uint32_t bar, int cnt) { asm volatile("mbarrier.init.shared::cta.b64 [%0], %1;" ::"r"(bar), "r"(cnt)); }
__device__ __forceinline__ void mbar_expect(uint32_t bar, int bytes) { asm volatile("mbarrier.arrive.expect_tx.shared::cta.b64 _, [%0], %1;" ::"r"(bar), "r"(bytes) : "memory"); }
__device__ __forceinline__ void mbar_arrive(uint32_t bar) { asm volatile("mbarrier.arrive.shared::cta.b64 _, [%0];" ::"r"(bar) : "memory"); }
__device__ __forceinline__ void mbar_arrive_cl(uint32_t bar, uint32_t cta) {
  asm volatile("{\n.reg .b32 r;\nmapa.shared::cluster.u32 r, %0, %1;\nmbarrier.arrive.shared::cluster.b64 _, [r];\n}\n" ::"r"(bar), "r"(cta) : "memory");
}
__device__ __forceinline__ void mbar_wait(uint32_t bar, uint32_t parity) {
  asm volatile("{\n.reg .pred p;\n.reg .u32 n;\nmov.u32 n, 0;\n"
               "W_%=:\nmbarrier.try_wait.parity.shared::cta.b64 p, [%0], %1;\n@p bra D_%=;\n"
               "add.u32 n, n, 1;\nsetp.lt.u32 p, n, %2;\n@p bra W_%=;\ntrap;\nD_%=:\n}\n" ::"r"(bar), "r"(parity), "n"(SPIN_LIMIT) : "memory");
}
__device__ __forceinline__ void fence_async() { asm volatile("fence.proxy.async.shared::cta;" ::: "memory"); }
__device__ __forceinline__ void bar_sync(int id) { asm volatile("bar.sync %0, 128;" ::"r"(id) : "memory"); }
__device__ __forceinline__ void tma2d(uint32_t dst, const CUtensorMap* m, int c0, int c1, uint32_t bar) {
  asm volatile("cp.async.bulk.tensor.2d.shared::cluster.global.mbarrier::complete_tx::bytes [%0], [%1, {%3, %4}], [%2];"
               ::"r"(dst), "l"(m), "r"(bar), "r"(c0), "r"(c1) : "memory");
}
__device__ __forceinline__ void tma2d_mc(uint32_t dst, const CUtensorMap* m, int c0, int c1, uint32_t bar) {
  asm volatile("cp.async.bulk.tensor.2d.shared::cluster.global.mbarrier::complete_tx::bytes.multicast::cluster [%0], [%1, {%3, %4}], [%2], %5;"
               ::"r"(dst), "l"(m), "r"(bar), "r"(c0), "r"(c1), "h"((uint16_t)3) : "memory");
}
__device__ __forceinline__ void tma3d(uint32_t dst, const CUtensorMap* m, int c0, int c1, int c2, uint32_t bar) {
  asm volatile("cp.async.bulk.tensor.3d.shared::cluster.global.mbarrier::complete_tx::bytes [%0], [%1, {%3, %4, %5}], [%2];"
               ::"r"(dst), "l"(m), "r"(bar), "r"(c0), "r"(c1), "r"(c2) : "memory");
}
__device__ __forceinline__ void bulk_ld(uint32_t dst, const void* src, int bytes, uint32_t bar) {
  asm volatile("cp.async.bulk.shared::cluster.global.mbarrier::complete_tx::bytes [%0], [%1], %2, [%3];" ::"r"(dst), "l"(src), "r"(bytes), "r"(bar) : "memory");
}
__device__ __forceinline__ void bulk_ld_mc(uint32_t dst, const void* src, int bytes, uint32_t bar) {
  asm volatile("cp.async.bulk.shared::cluster.global.mbarrier::complete_tx::bytes.multicast::cluster [%0], [%1], %2, [%3], %4;"
               ::"r"(dst), "l"(src), "r"(bytes), "r"(bar), "h"((uint16_t)3) : "memory");
}
__device__ __forceinline__ void tma2d_st(const CUtensorMap* m, uint32_t src, int c0, int c1) {
  asm volatile("cp.async.bulk.tensor.2d.global.shared::cta.bulk_group [%0, {%2, %3}], [%1];" ::"l"(m), "r"(src), "r"(c0), "r"(c1) : "memory");
}
__device__ __forceinline__ void pf_l2(const void* p, int bytes) { asm volatile("cp.async.bulk.prefetch.L2.global [%0], %1;" ::"l"(p), "r"(bytes) : "memory"); }
__device__ __forceinline__ void pf_t2d(const CUtensorMap* m, int c0, int c1) {
  asm volatile("cp.async.bulk.prefetch.tensor.2d.L2.global [%0, {%1, %2}];" ::"l"(m), "r"(c0), "r"(c1) : "memory");
}
__device__ __forceinline__ void pf_t3d(const CUtensorMap* m, int c0, int c1, int c2) {
  asm volatile("cp.async.bulk.prefetch.tensor.3d.L2.global [%0, {%1, %2, %3}];" ::"l"(m), "r"(c0), "r"(c1), "r"(c2) : "memory");
}
__device__ __forceinline__ void ldsm4(uint32_t (&r)[4], uint32_t a) {
  asm volatile("ldmatrix.sync.aligned.m8n8.x4.shared.b16 {%0,%1,%2,%3}, [%4];" : "=r"(r[0]), "=r"(r[1]), "=r"(r[2]), "=r"(r[3]) : "r"(a) : "memory");
}
__device__ __forceinline__ void ldsm4t(uint32_t (&r)[4], uint32_t a) {
  asm volatile("ldmatrix.sync.aligned.m8n8.x4.trans.shared.b16 {%0,%1,%2,%3}, [%4];" : "=r"(r[0]), "=r"(r[1]), "=r"(r[2]), "=r"(r[3]) : "r"(a) : "memory");
}
__device__ __forceinline__ void stsm4(uint32_t a, uint32_t r0, uint32_t r1, uint32_t r2, uint32_t r3) {
  asm volatile("stmatrix.sync.aligned.m8n8.x4.shared.b16 [%0], {%1,%2,%3,%4};" ::"r"(a), "r"(r0), "r"(r1), "r"(r2), "r"(r3) : "memory");
}
__device__ __forceinline__ uint32_t pk2(float lo, float hi) { uint32_t r; asm("cvt.rn.bf16x2.f32 %0, %1, %2;" : "=r"(r) : "f"(hi), "f"(lo)); return r; }
__device__ __forceinline__ uint32_t hmul(uint32_t a, uint32_t b) { uint32_t r; asm("mul.rn.bf16x2 %0, %1, %2;" : "=r"(r) : "r"(a), "r"(b)); return r; }
__device__ __forceinline__ uint32_t hadd(uint32_t a, uint32_t b) { uint32_t r; asm("add.rn.bf16x2 %0, %1, %2;" : "=r"(r) : "r"(a), "r"(b)); return r; }
__device__ __forceinline__ uint32_t hmax(uint32_t a, uint32_t b) { uint32_t r; asm("max.bf16x2 %0, %1, %2;" : "=r"(r) : "r"(a), "r"(b)); return r; }
__device__ __forceinline__ uint32_t hmin(uint32_t a, uint32_t b) { uint32_t r; asm("min.bf16x2 %0, %1, %2;" : "=r"(r) : "r"(a), "r"(b)); return r; }
__device__ __forceinline__ uint32_t hmaxabs(uint32_t a, uint32_t b) { uint32_t r; asm("max.xorsign.abs.bf16x2 %0, %1, %2;" : "=r"(r) : "r"(a), "r"(b)); return r; }
__device__ __forceinline__ float ex2(float x) { float r; asm("ex2.approx.ftz.f32 %0, %1;" : "=f"(r) : "f"(x)); return r; }
__device__ __forceinline__ float rcp_fast(float x) { float r; asm("rcp.approx.ftz.f32 %0, %1;" : "=f"(r) : "f"(x)); return r; }
__device__ __forceinline__ uint32_t phi2(float lo, float hi) {
  uint32_t t = pk2(lo, hi);
  uint32_t e = pk2(ex2(lo * 1.4426950408889634f), ex2(hi * 1.4426950408889634f));
  return hadd(hmax(t, 0x35863586u), hmin(e, 0x3F803F80u));
}
__device__ __forceinline__ void poll_ge(const unsigned* p, unsigned target) {
#pragma unroll 1
  for (int n = 0; n < SPIN_LIMIT; n++) {
    unsigned v;
    asm volatile("ld.acquire.gpu.global.u32 %0, [%1];" : "=r"(v) : "l"(p) : "memory");
    if ((int)(v - target) >= 0) return;
  }
  __trap();
}

__device__ __forceinline__ bool elect_one() {
  uint32_t p;
  asm volatile("{\n.reg .pred p;\nelect.sync _|p, 0xffffffff;\nselp.u32 %0, 1, 0, p;\n}\n" : "=r"(p));
  return p;
}
__device__ __forceinline__ uint32_t mapa(uint32_t a, uint32_t cta) { uint32_t r; asm("mapa.shared::cluster.u32 %0, %1, %2;" : "=r"(r) : "r"(a), "r"(cta)); return r; }
__device__ __forceinline__ void st_async(uint32_t a, uint32_t v, uint32_t bar) {
  asm volatile("st.async.weak.shared::cluster.mbarrier::complete_tx::bytes.b32 [%0], %1, [%2];" ::"r"(a), "r"(v), "r"(bar) : "memory");
}
__device__ __forceinline__ void st_async4(uint32_t a, uint32_t x, uint32_t y, uint32_t z, uint32_t w, uint32_t bar) {
  asm volatile("st.async.weak.shared::cluster.mbarrier::complete_tx::bytes.v4.b32 [%0], {%1,%2,%3,%4}, [%5];" ::"r"(a), "r"(x), "r"(y), "r"(z), "r"(w), "r"(bar) : "memory");
}
__device__ __forceinline__ void tma3d_st(const CUtensorMap* m, uint32_t src, int c0, int c1, int c2) {
  asm volatile("cp.async.bulk.tensor.3d.global.shared::cta.bulk_group [%0, {%2, %3, %4}], [%1];" ::"l"(m), "r"(src), "r"(c0), "r"(c1), "r"(c2) : "memory");
}
__device__ __forceinline__ uint4 ld_rlx4(const void* p) {
  uint4 v;
  asm volatile("{\n.reg .b128 t;\n.reg .b64 a, b;\nld.relaxed.gpu.global.b128 t, [%4];\nmov.b128 {a, b}, t;\nmov.b64 {%0, %1}, a;\nmov.b64 {%2, %3}, b;\n}\n"
               : "=r"(v.x), "=r"(v.y), "=r"(v.z), "=r"(v.w) : "l"(p) : "memory");
  return v;
}
__device__ __forceinline__ void st_tag4(void* p, float a, float b, float c, float d, uint32_t tag) {
  asm volatile("{\n.reg .b128 t;\n.reg .b64 a, b;\nmov.b64 a, {%1, %2};\nmov.b64 b, {%3, %4};\nmov.b128 t, {a, b};\nst.relaxed.gpu.global.b128 [%0], t;\n}\n"
               ::"l"(p), "r"((__float_as_uint(a) & ~1u) | tag), "f"(b), "f"(c), "f"(d) : "memory");
}
__device__ __forceinline__ uint32_t stale8(const uint4 (&f)[8], uint32_t tag) {
  uint32_t r[4];
#pragma unroll
  for (int i = 0; i < 4; i++) asm("lop3.b32 %0, %1, %2, %3, 0x7E;" : "=r"(r[i]) : "r"(f[2 * i].x), "r"(f[2 * i + 1].x), "r"(tag));
  asm("lop3.b32 %0, %0, %1, %2, 0xFE;" : "+r"(r[0]) : "r"(r[1]), "r"(r[2]));
  return r[0] | r[3];
}

struct ConvC { uint32_t a1[2][4], wa[2], wb[2], sg; };
__device__ __forceinline__ uint64_t dsc(uint32_t lo, uint32_t hi) { return ((uint64_t)hi << 32) | lo; }
__device__ __forceinline__ uint32_t hfma(uint32_t a, uint32_t b, uint32_t c) { uint32_t r; asm("fma.rn.f16x2 %0, %1, %2, %3;" : "=r"(r) : "r"(a), "r"(b), "r"(c)); return r; }
__device__ __forceinline__ uint32_t hfnma(uint32_t a, uint32_t b, uint32_t c) { uint32_t r; asm("{.reg .b32 n; neg.f16x2 n, %1; fma.rn.f16x2 %0, n, %2, %3;}" : "=r"(r) : "r"(a), "r"(b), "r"(c)); return r; }
__device__ __forceinline__ uint32_t hmul16(uint32_t a, uint32_t b) { uint32_t r; asm("mul.rn.f16x2 %0, %1, %2;" : "=r"(r) : "r"(a), "r"(b)); return r; }
template <int N> __device__ __forceinline__ void keepu(uint32_t (&d)[N]) {
#pragma unroll
  for (int i = 0; i < N; i++) asm volatile("" : "+r"(d[i])::"memory");
}
__device__ __forceinline__ void conv_m1(const ConvC& K, uint32_t (&u)[16], uint32_t l) {
  wg_fence();
#pragma unroll
  for (int s = 0; s < 2; s++) wgmma_hrs_n64<1>(u, K.a1[s][0], K.a1[s][1], K.a1[s][2], K.a1[s][3], dsc(l + s * 16, 32), s);
  wg_commit();
}
__device__ __forceinline__ void conv_s2(const ConvC& K, uint32_t (&u)[16], uint32_t (&Z)[2][8], uint32_t dfl) {
  uint32_t fr[8], fi[8];
#pragma unroll
  for (int c = 0; c < 8; c++) {
    const uint32_t r = hfma(K.wa[c & 1], u[2 * c + 1], u[2 * c]);
    fi[c] = hfma(K.wb[c & 1], r, u[2 * c + 1]);
    fr[c] = hfma(K.wa[c & 1], fi[c], r);
  }
  wg_fence();
#pragma unroll
  for (int p = 0; p < 2; p++) {
    wgmma_hrs_n32<0>(Z[p], fr[4 * p], fr[4 * p + 2], fr[4 * p + 1], fr[4 * p + 3], dsc(dfl, 32), 0);
    wgmma_hrs_n32<0>(Z[p], fi[4 * p], fi[4 * p + 2], fi[4 * p + 1], fi[4 * p + 3], dsc(dfl + 16, 32), 1);
  }
  wg_commit();
}
__device__ __forceinline__ void conv_win(const ConvC& K, uint32_t (&X)[2][8]) {
#pragma unroll
  for (int b = 3; b >= 1; b--)
#pragma unroll
    for (int c = 0; c < 2; c++) {
      uint32_t& xr = X[b >> 1][2 * c + (b & 1)]; uint32_t& xi = X[b >> 1][4 + 2 * c + (b & 1)];
      xr = hfnma(K.sg, X[(b - 1) >> 1][4 + 2 * c + ((b - 1) & 1)], xr);
      xi = hfma(K.sg, X[(b - 1) >> 1][2 * c + ((b - 1) & 1)], xi);
    }
}
template <int p>
__device__ __forceinline__ void conv_pw(uint32_t (&X)[2][8], uint32_t (&H)[2][8], uint32_t (&V)[8], uint32_t dil) {
  uint32_t pr[2][2], pi[2][2];
#pragma unroll
  for (int jj = 0; jj < 2; jj++)
#pragma unroll
    for (int c = 0; c < 2; c++) {
      const int j = 2 * p + jj;
      uint32_t sr = 0, si = 0;
#pragma unroll
      for (int a = 0; a <= j; a++) {
        const int b = j - a;
        const uint32_t hr = H[a >> 1][2 * c + (a & 1)], hi = H[a >> 1][4 + 2 * c + (a & 1)];
        const uint32_t xr = X[b >> 1][2 * c + (b & 1)], xi = X[b >> 1][4 + 2 * c + (b & 1)];
        sr = a == 0 ? hmul16(hr, xr) : hfma(hr, xr, sr);
        si = a == 0 ? hmul16(hr, xi) : hfma(hr, xi, si);
        sr = hfnma(hi, xi, sr);
        si = hfma(hi, xr, si);
      }
      pr[jj][c] = sr; pi[jj][c] = si;
    }
  wg_fence();
  wgmma_hrs_n32<0>(V, pr[0][0], pr[1][0], pr[0][1], pr[1][1], dsc(dil, 32), 0);
  wgmma_hrs_n32<0>(V, pi[0][0], pi[1][0], pi[0][1], pi[1][1], dsc(dil + 16, 32), 1);
  wg_commit();
}
template <int p>
__device__ __forceinline__ void conv_it(const ConvC& K, uint32_t (&V)[8], uint32_t vst) {
#pragma unroll
  for (int jj = 0; jj < 2; jj++) {
    uint32_t wr[2], wi[2];
#pragma unroll
    for (int c = 0; c < 2; c++) {
      const uint32_t r = hfnma(K.wa[c], V[4 + 2 * c + jj], V[2 * c + jj]);
      wi[c] = hfnma(K.wb[c], r, V[4 + 2 * c + jj]);
      wr[c] = hfnma(K.wa[c], wi[c], r);
    }
    stsm4(vst + (2 * p + jj) * 2048, wr[0], wr[1], wi[0], wi[1]);
  }
}
__device__ __forceinline__ void conv_m4(uint32_t (&y)[8], uint32_t (&a)[4][4], uint32_t d4l) {
  wg_fence();
#pragma unroll
  for (int s = 0; s < 4; s++) wgmma_hrs_n32<0>(y, a[s][0], a[s][1], a[s][2], a[s][3], dsc(d4l + s * 16, 64), s);
  wg_commit();
}

struct Params {
  CUtensorMap tmX, tmW, tmWo, tmK, tmV, tmQ, tmOA, tmOB;
  const __nv_bfloat16 *shift_k, *h, *D, *x, *w, *wo;
};

__global__ void __cluster_dims__(2, 1, 1) __launch_bounds__(384, 1) fused_kernel(const __grid_constant__ Params P) {
  extern __shared__ __align__(1024) uint8_t smem[];
  const uint32_t sb = smem_u32(smem);
  const uint32_t bars = sb + OFF_BAR;
  const int tid = threadIdx.x, lane = tid & 31;
  const int warp = __shfl_sync(~0u, tid >> 5, 0);
  const int rank = blockIdx.x & 1, cl = blockIdx.x >> 1;
  const int mb = cl >> 3, hq = cl & 7;
  const int hp = 2 * hq + rank;
  const int rb = 2 * mb + (hq >> 2), cb = hq & 3;
#define BAR(i) (bars + 8 * (i))

  if (tid == 0) { STAMP(0, 0); GSTAMP(0, 30); }
  if (lane == 0) {
#pragma unroll
    for (int r = 0; r < 6; r++)
      if (r < 5 || warp < B_COUNT - 60) mbar_init(BAR(12 * r + warp), ((uint32_t)(bar_counts(r) >> (4 * warp)) & 15) + 1);
    asm volatile("fence.mbarrier_init.release.cluster;" ::: "memory");
  }
  asm volatile("barrier.cluster.arrive.relaxed.aligned;\nbarrier.cluster.wait.aligned;" ::: "memory");

  if (warp < 8) {
    asm volatile("setmaxnreg.inc.sync.aligned.u32 224;");
    const int wg = warp >> 2, w = warp & 3, g = lane >> 2, q = lane & 3, t = tid & 127;
    const bool elect = (t == 0);
    const uint32_t s16 = (sb & 0x3FFFF) >> 4;
    constexpr uint32_t SW128 = 64 | (1u << 30);
    uint32_t pq[2][16], v[32];
    float fd;
    ConvC K;
    {
      float acc[2][96];
      int st = 0, ph = 0;
#pragma unroll 1
      for (int kb = 0; kb < 16; kb++) {
        mbar_wait(BAR(B_FULL1 + st), ph);
        if (kb == 0 && elect) { STAMP(wg, 1); GSTAMP(wg, 26); }
        if (kb == 8 && elect) { STAMP(wg, 16); GSTAMP(wg, 25); }
        const uint32_t da = s16 + st * (STAGE_BYTES >> 4) + wg * 1024 + (1 << 16);
        const uint32_t db = s16 + st * (STAGE_BYTES >> 4) + 2048 + (512 << 16);
        wg_fence();
#pragma unroll
        for (int ks = 0; ks < 4; ks++) {
          wgmma_ss_n192<0, 1>(acc[0], dsc(da + ks * 2, SW128), dsc(db + ks * 128, SW128), (kb | ks) != 0);
          wgmma_ss_n192<0, 1>(acc[1], dsc(da + 512 + ks * 2, SW128), dsc(db + ks * 128, SW128), (kb | ks) != 0);
        }
        wg_commit();
        wg_wait<1>();
        if (kb > 0 && t < 2) mbar_arrive_cl(BAR(B_EMPTY1 + (st == 0 ? 2 : st - 1)), t);
        if (++st == 3) { st = 0; ph ^= 1; }
      }
      wg_wait<0>();
      keep(acc[0]); keep(acc[1]);
      if (t < 2) mbar_arrive_cl(BAR(B_EMPTY1 + 0), t);
      if (elect) { STAMP(wg, 2); GSTAMP(wg, 27); }
      const uint32_t lrow = sb + wg * 16384 + (16 * w + 8 * ((lane >> 3) & 1) + (lane & 7)) * 128 + (((lane >> 4) ^ (lane & 7)) << 4);
#pragma unroll
      for (int mt = 0; mt < 2; mt++)
#pragma unroll
        for (int cp = 0; cp < 4; cp++) {
          const float* a = &acc[mt][32 + 8 * cp];
          const float* b = &acc[mt][64 + 8 * cp];
          const uint32_t o = (lrow ^ (cp * 32)) + mt * 8192;
          stsm4(o + OFF_PK, phi2(a[0], a[1]), phi2(a[2], a[3]), phi2(a[4], a[5]), phi2(a[6], a[7]));
          stsm4(o + OFF_V, pk2(b[0], b[1]), pk2(b[2], b[3]), pk2(b[4], b[5]), pk2(b[6], b[7]));
        }
      fence_async();
      mbar_wait(BAR(B_XT), 0);
      {
        const uint4* ct = (const uint4*)c_thr + t;
#pragma unroll
        for (int s = 0; s < 2; s++) { uint4 u = __ldg(ct + s * 128); K.a1[s][0] = u.x; K.a1[s][1] = u.y; K.a1[s][2] = u.z; K.a1[s][3] = u.w; }
        uint4 u = __ldg(ct + 2 * 128);
        K.wa[0] = u.x; K.wa[1] = u.y; K.wb[0] = u.z; K.wb[1] = u.w;
        K.sg = (lane & 4) ? 0xBC00BC00u : 0x3C003C00u;
      }
      const int ch = blockIdx.x * 8 + warp;
      float f0 = 0.f;
      if (lane == 0) f0 = __bfloat162float(P.D[ch]);
#pragma unroll
      for (int i = 0; i < 8; i++) {
        const uint4 u = __ldg((const uint4*)(P.h + ch * 2048) + i * 32 + (lane & 15) * 2 + (lane >> 4));
        v[4 * i] = u.x; v[4 * i + 1] = u.y; v[4 * i + 2] = u.z; v[4 * i + 3] = u.w;
      }
      fd = f0;
      if (wg == 0) {
        asm volatile("bar.sync 3, 256;" ::: "memory");
        if (elect) STAMP(wg, 3);
        float kva[36];
        wg_fence();
#pragma unroll
        for (int ks = 0; ks < 16; ks++)
          wgmma_ss_n72<1, 1>(kva, dsc(s16 + (OFF_PK >> 4) + ks * 128 + (1 << 16), SW128),
                             dsc(s16 + (OFF_V >> 4) + ks * 128 + (((OFF_ONES - OFF_V - ks * 2048) >> 4) << 16), SW128), ks != 0);
        wg_commit();
        const uint32_t tag = ~*(volatile unsigned*)(smem + OFF_EPOCH) & 1;
        float* dst = &g_part[hp][mb][0];
        wg_wait<0>();
        keep(kva);
#pragma unroll
        for (int c = 0; c < 4; c++)
          st_tag4(dst + (c * 128 + t) * 4, w < 2 ? kva[4 * c] : kva[16 + 4 * c], w < 2 ? kva[4 * c + 1] : kva[17 + 4 * c],
                  w < 2 ? kva[4 * c + 2] : kva[18 + 4 * c], w < 2 ? kva[4 * c + 3] : kva[19 + 4 * c], tag);
        {
          const float z2 = __shfl_down_sync(~0u, kva[32], 4), z3 = __shfl_down_sync(~0u, kva[34], 4);
          if (!(lane & 7)) st_tag4(dst + 2048 + 16 * w + 2 * g, kva[32], kva[34], z2, z3, tag);
        }
        if (lane == 0) mbar_arrive(BAR(B_PKFREE));
      } else {
        asm volatile("bar.arrive 3, 256;" ::: "memory");
      }
      if (elect) STAMP(wg, 4);
#pragma unroll
      for (int mt = 0; mt < 2; mt++)
#pragma unroll
        for (int i = 0; i < 16; i++) pq[mt][i] = phi2(acc[mt][2 * i], acc[mt][2 * i + 1]);
      keepu(pq[0]); keepu(pq[1]);
    }
    mbar_wait(BAR(B_EMPTY1 + 2), 0);
    if (elect) STAMP(wg, 17);
    {
      mbar_wait(BAR(B_XRAW), 0);
      uint8_t* dst = smem + OFF_H + (w & 2) * 8192 + wg * 8192 + (w & 1) * 4096 + (lane >> 4) * 512 + (lane & 15) * 16;
      int es = -124;
#pragma unroll 1
      for (int job = 0; job < 2; job++) {
        const float f0 = fd + __uint_as_float(v[0] << 16);
        uint32_t m[4] = {hmaxabs(__float_as_uint(f0) >> 16, v[0]), v[1], v[2], v[3]};
#pragma unroll
        for (int i = 4; i < 32; i++) m[i & 3] = hmaxabs(m[i & 3], v[i]);
        m[0] = hmaxabs(hmaxabs(m[0], m[1]), hmaxabs(m[2], m[3]));
        const int e = min(max((int)(__reduce_max_sync(~0u, max(m[0] & 0x7FFFu, (m[0] >> 16) & 0x7FFFu)) >> 7), 1), 253);
        es += e;
        if (e > 141) {
#pragma unroll
          for (int i = 0; i < 32; i++) v[i] = hmul(v[i], 0x07000700u);
        }
        const uint32_t sc = (e > 141 ? 255 - e : 142 - e) * 0x00800080u;
#pragma unroll
        for (int i = 0; i < 32; i++) {
          const uint32_t a = hmul(v[i], sc);
          v[i] = (a & 0x0FFF0FFFu) * 7 + a;
        }
        v[0] = __byte_perm(v[0], __half_as_ushort(__float2half_rn(f0 * __uint_as_float((254 - e) << 23))), 0x3254);
        uint8_t* nxt = smem + OFF_XT + warp * XT_STRIDE + (lane >> 4) * 512 + (lane & 15) * 16;
#pragma unroll
        for (int i = 0; i < 8; i++) {
          *(uint4*)(dst + (i >> 1) * 1024 + (i & 1) * 256) = make_uint4(v[4 * i], v[4 * i + 1], v[4 * i + 2], v[4 * i + 3]);
          if (job == 0) {
            const uint4 u = *(const uint4*)(nxt + (i >> 1) * 1024 + (i & 1) * 256);
            v[4 * i] = u.x; v[4 * i + 1] = u.y; v[4 * i + 2] = u.z; v[4 * i + 3] = u.w;
          }
        }
        dst = nxt;
        fd = 0.f;
      }
      if (lane < 2) st_async(mapa(sb + OFF_SCALE + (8 * rank + warp) * 4, lane), min(max(es, 1), 254) << 23, mapa(BAR(B_Y), lane));
      fence_async();
      bar_sync(1 + wg);
    }
    if (elect) STAMP(wg, 5);
    {
      const uint32_t dfl = s16 + (OFF_F2F >> 4) + (8 << 16), dil = s16 + (OFF_F2I >> 4) + (8 << 16), d4l = s16 + (OFF_F4 >> 4) + (8 << 16);
      const uint32_t xl = s16 + (OFF_XT >> 4) + 4 * wg * (XT_STRIDE >> 4) + (8 << 16);
      const uint32_t hl = s16 + (OFF_H >> 4) + wg * 512 + (8 << 16);
      uint32_t vst = sb + wg * 8192 + w * 512 + lane * 16, vld = sb + wg * 8192 + w * 2048 + lane * 16;
      uint32_t ya = mapa(sb + OFF_XT + 4 * wg * XT_STRIDE + (2 * rank + (w & 1)) * 1024 + lane * 16, w >> 1);
      const uint32_t ybar = mapa(BAR(B_Y), w >> 1);
      asm volatile("" : "+r"(vst), "+r"(vld), "+r"(ya));
      uint32_t ux[16], uh[16], X[4][2][8], H[4][2][8], V0[8], V1[8], y[8], a[4][4];
#define YOUT(i) do { mbar_wait(BAR(B_XFREE + 4 * wg + (i)), 0); \
        st_async4(ya + (i) * XT_STRIDE, y[0], y[2], y[4], y[6], ybar); \
        st_async4(ya + (i) * XT_STRIDE + 512, y[1], y[3], y[5], y[7], ybar); } while (0)
      conv_m1(K, ux, xl);
      conv_m1(K, uh, hl);
      wg_wait<1>(); keepu(ux);
      if (lane == 0) mbar_arrive_cl(BAR(B_XFREE + 4 * wg), rank ^ 1);
      conv_s2(K, ux, X[0], dfl);
      wg_wait<1>(); keepu(uh);
      conv_s2(K, uh, H[0], dfl);
#pragma unroll
      for (int i = 0; i < 4; i++) {
        const bool nx = i < 3;
        const int n = nx ? i + 1 : i;
        const uint32_t vo = (i & 1) ? OFF_H + (i >> 1) * 16384 : OFF_VP;
        float oa[4][20];
        if (i == OC) {
          if (elect) STAMP(wg, 8);
          mbar_wait(BAR(B_KV), 0);
          if (elect) STAMP(wg, 9);
          wg_wait<0>();
          wg_fence();
#pragma unroll
          for (int m = 0; m < 8; m++) {
            const uint32_t* p = &pq[m >> 2][4 * (m & 3)];
            wgmma_rs_n40<1>(oa[m >> 1], p[0], p[1], p[2], p[3], dsc(s16 + (OFF_KVB >> 4) + ((m >> 1) & 1) * 160 + (m & 1) * 16 + (8 << 16), 32), m & 1);
          }
          wg_commit();
        }
        if (nx) {
          conv_m1(K, ux, xl + n * (XT_STRIDE >> 4));
          conv_m1(K, uh, hl + (n >> 1) * 1024 + (n & 1) * 256);
        }
        if (i == OC) { if (nx) wg_wait<2>(); else wg_wait<0>(); }
        else if (nx) { if (i > 0) wg_wait<3>(); else wg_wait<2>(); }
        else wg_wait<1>();
        if (i == OC) {
          uint4* ot = g_o + ((2 * mb + wg) * 16 + hp) * 1024 + (16 * w + g) * 8;
#pragma unroll
          for (int m = 0; m < 4; m++) {
            float (&o)[20] = oa[m];
            keep(o);
            const uint32_t den = hadd(pk2(o[16], o[18]), 0x35863586u);
#pragma unroll
            for (int r = 0; r < 2; r++) {
              const float ri = rcp_fast(__uint_as_float(r ? (den & 0xFFFF0000u) : (den << 16)));
              uint4 u;
              u.x = pk2(o[2 * r] * ri, o[2 * r + 1] * ri);
              u.y = pk2(o[4 + 2 * r] * ri, o[5 + 2 * r] * ri);
              u.z = pk2(o[8 + 2 * r] * ri, o[9 + 2 * r] * ri);
              u.w = pk2(o[12 + 2 * r] * ri, o[13 + 2 * r] * ri);
              __stcg(ot + (64 * (m >> 1) + 8 * r) * 8 + ((4 * (m & 1) + q) ^ g), u);
            }
          }
          __syncwarp();
          if (lane == 0) mbar_arrive(BAR(B_ODONE));
          if (elect) STAMP(wg, 10);
        }
        keepu(X[i][0]); keepu(X[i][1]); keepu(H[i][0]); keepu(H[i][1]);
        conv_win(K, X[i]);
        conv_pw<0>(X[i], H[i], V0, dil);
        conv_pw<1>(X[i], H[i], V1, dil);
        wg_wait<2>();
        if (i > 0) { keepu(y); YOUT(i - 1); }
        if (nx) {
          keepu(ux); keepu(uh);
          if (lane == 0) mbar_arrive_cl(BAR(B_XFREE + 4 * wg + n), rank ^ 1);
          conv_s2(K, ux, X[n], dfl);
          wg_wait<1>();
        } else wg_wait<0>();
        keepu(V0); keepu(V1);
        conv_it<0>(K, V0, vst + vo);
        conv_it<1>(K, V1, vst + vo);
        bar_sync(1 + wg);
#pragma unroll
        for (int s = 0; s < 4; s++) ldsm4t(a[s], vld + vo + s * 512);
        if (nx) conv_s2(K, uh, H[n], dfl);
        conv_m4(y, a, d4l);
        if (i > 0 && lane < 2) mbar_arrive_cl(BAR(B_AFREE + i - 1), lane);
        if (elect) STAMP(wg, i < 2 ? 6 + i : 9 + i);
      }
      wg_wait<0>(); keepu(y);
      YOUT(3);
    }
    {
      float acc[64];
#pragma unroll 1
      for (int kb = 0; kb < 16; kb++) {
        mbar_wait(BAR(B_FULL2 + kb), 0);
        if (kb == 0 && elect) { STAMP(wg, 13); GSTAMP(wg, 28); }
        const uint32_t da = s16 + ((uint32_t)(SLOT_A >> (4 * kb)) & 15) * 1024 + wg * 512 + (1 << 16);
        const uint32_t db = s16 + ((uint32_t)(SLOT_B >> (4 * kb)) & 15) * 1024 + (512 << 16);
        wg_fence();
#pragma unroll
        for (int ks = 0; ks < 4; ks++) wgmma_ss_n128<0, 1>(acc, dsc(da + ks * 2, SW128), dsc(db + ks * 128, SW128), (kb | ks) != 0);
        wg_commit();
        wg_wait<1>();
        if (kb > 0 && kb < 14 && t < 2 && (kb <= 11 || t == rank)) mbar_arrive_cl(BAR(B_CONS2 + kb - 1), t);
      }
      wg_wait<0>();
      keep(acc);
      if (elect) { STAMP(wg, 14); GSTAMP(wg, 29); }
      mbar_wait(BAR(B_CONS2 + 12), 0);
      const uint32_t stg = sb + (wg ? 5 : 3) * 16384;
      const uint32_t lrow = stg + (16 * w + 8 * ((lane >> 3) & 1) + (lane & 7)) * 128 + (((lane >> 4) ^ (lane & 7)) << 4);
#pragma unroll
      for (int cp = 0; cp < 8; cp++) {
        const float* a = &acc[8 * cp];
        stsm4((lrow ^ ((cp & 3) * 32)) + (cp >> 2) * 8192, pk2(a[0], a[1]), pk2(a[2], a[3]), pk2(a[4], a[5]), pk2(a[6], a[7]));
      }
      fence_async();
      bar_sync(1 + wg);
      if (elect) {
        const int col = 1024 + 256 * cb + 128 * rank, row = 128 * rb + 64 * wg;
        tma2d_st(&P.tmOB, stg, col, row);
        tma2d_st(&P.tmOB, stg + 8192, col + 64, row);
        asm volatile("cp.async.bulk.commit_group;\ncp.async.bulk.wait_group.read 0;" ::: "memory");
        STAMP(wg, 15); GSTAMP(wg, 31);
      }
    }
  } else {
    asm volatile("setmaxnreg.dec.sync.aligned.u32 56;");
    if (warp == 8) {
      int st = 0, ph = 1;
      const uint8_t* pfx = (const uint8_t*)P.x + (mb * 256 + hp * 16 + (lane & 15)) * 2048;
      const uint8_t* pfw = (const uint8_t*)P.w + (mb * 8 + (lane & 7)) * 6144 + (lane >> 3) * 2048 + hp * 128;
#pragma unroll 1
      for (int kb = 0; kb < 16; kb++) {
        if (kb >= 3) mbar_wait(BAR(B_EMPTY1 + st), ph);
        const uint32_t sa = sb + st * STAGE_BYTES;
        if (elect_one()) {
          mbar_expect(BAR(B_FULL1 + st), STAGE_BYTES);
          tma2d_mc(sa + rank * 16384, &P.tmX, kb * 64, mb * 256 + rank * 128, BAR(B_FULL1 + st));
          tma3d(sa + 32768, &P.tmW, hp * 64, kb * 64, 0, BAR(B_FULL1 + st));
        }
        if (PFD && kb >= 2) {
#pragma unroll 1
          for (int j = kb == 2 ? 3 : kb + PFD; j <= kb + PFD && j < 16; j++) {
            if (lane < 16) asm volatile("prefetch.global.L2 [%0];" ::"l"(pfx + j * 128));
            if (lane < 24) asm volatile("prefetch.global.L2 [%0];" ::"l"(pfw + j * (64 * 6144)));
          }
          if (kb >= 8 && kb < 12) asm volatile("prefetch.global.L2 [%0];" ::"l"((const uint8_t*)P.wo + (blockIdx.x * 128 + (kb - 8) * 32 + lane) * 128));
        }
        if (++st == 3) { st = 0; ph ^= 1; }
      }
      if (lane == 0) STAMP(2, 1);
      const unsigned epoch = g_epoch[blockIdx.x];
#define SLOT(tab, kb) (sb + ((uint32_t)((tab) >> (4 * (kb))) & 15) * 16384)
#define LOAD_B(kb) tma3d(SLOT(SLOT_B, kb), &P.tmWo, 0, (kb) * 64, 4 * cb + 2 * rank, BAR(B_FULL2 + (kb)))
#define LOAD_A(kb) bulk_ld_mc(SLOT(SLOT_A, kb) + rank * 8192, g_o + (rb * 16 + (kb)) * 1024 + rank * 512, 8192, BAR(B_FULL2 + (kb)))
      mbar_wait(BAR(B_EMPTY1 + 1), 0);
#pragma unroll 1
      for (int kb = 0; kb < 7; kb++) {
        if (kb == 1) mbar_wait(BAR(B_EMPTY1 + 0), 1);
        if (kb == 3) mbar_wait(BAR(BPRE), 0);
        if (elect_one()) { mbar_expect(BAR(B_FULL2 + kb), 16384); LOAD_B(kb); }
      }
      if (lane == 0) STAMP(2, 2);
      poll_ge(&g_ocnt[rb * 32], 16 * (epoch + 1));
      asm volatile("fence.proxy.async.global;" ::: "memory");
      if (lane == 0) STAMP(2, 3);
#pragma unroll 1
      for (int kb = 0; kb < 7; kb++) {
        mbar_wait(BAR(kb < 3 ? B_AFREE + kb : B_CONS2 + ((kb - 3) >> 1)), 0);
        if (elect_one()) { mbar_expect(BAR(B_FULL2 + kb), 16384); LOAD_A(kb); }
        if (kb == 2 && lane == 0) STAMP(2, 4);
      }
#pragma unroll 1
      for (int kb = 7; kb < 16; kb++) {
        mbar_wait(BAR(B_CONS2 + kb - 5), 0);
        if (elect_one()) { mbar_expect(BAR(B_FULL2 + kb), 32768); LOAD_A(kb); LOAD_B(kb); }
      }
      if (lane == 0) { g_epoch[blockIdx.x] = epoch + 1; STAMP(2, 5); }
    } else {
      const int hw = warp - 9, g = lane >> 2, q = lane & 3;
      const unsigned epoch = g_epoch[blockIdx.x];
      const uint32_t tag = ~epoch & 1;
      const uint32_t stg = sb + OFF_STG + hw * STG_STRIDE, sbar = BAR(B_STG + 2 * hw);
      int ph = 0;
      {
        uint32_t tap[2][4];
#pragma unroll
        for (int cg = 0; cg < 2; cg++) {
          const uint2 u = __ldg((const uint2*)(P.shift_k + (16 * cl + 8 * cg + g) * 4));
          tap[cg][0] = __byte_perm(u.x, 0, 0x1010); tap[cg][1] = __byte_perm(u.x, 0, 0x3232);
          tap[cg][2] = __byte_perm(u.y, 0, 0x1010); tap[cg][3] = __byte_perm(u.y, 0, 0x3232);
        }
        __nanosleep(HDELAY);
        if (hw == 0 && elect_one()) {
          *(volatile unsigned*)(smem + OFF_EPOCH) = epoch;
          mbar_expect(BAR(B_XRAW), 32768);
          mbar_expect(BAR(B_Y), 32768 + 64);
        }
        if (lane == 0) STAMP(3, hw);
        const uint32_t xo = sb + OFF_XT + g * XT_STRIDE + rank * 2048 + q * 4;
        const int krow = 8 + (lane & 7) - (lane >> 3);
        const uint32_t ka = stg + krow * 32 + ((krow & 4) << 2), va = stg + 2304 + lane * 32 + ((lane & 4) << 2);
        int b = 0;
#pragma unroll 1
        for (int ci = hw - 6; ci < 16; ci += 3) {
          const uint32_t bo = b ? OFF_F2F - OFF_STG : 0;
          if (ci >= 0) {
            mbar_wait(sbar + 8 * b, (ph >> b) & 1);
            ph ^= 1 << b;
#pragma unroll 1
            for (int grp = 0; grp < 2; grp++) {
#pragma unroll
              for (int cg = 0; cg < 2; cg++) {
                const uint32_t dst = mapa(xo + (ci >> 3) * 1024 + ((ci & 7) * 4 + 2 * grp) * 16, cg), xbar = mapa(BAR(B_XRAW), cg);
                uint32_t vv[4], kk[4][4];
                ldsm4t(vv, (va ^ (cg * 16)) + bo + grp * 1024);
#pragma unroll
                for (int rg = 0; rg < 4; rg++) ldsm4t(kk[rg], (ka ^ (cg * 16)) + bo + grp * 1024 + rg * 256);
#pragma unroll
                for (int rg = 0; rg < 4; rg++)
                  vv[rg] = hmul(hadd(hadd(hadd(hmul(kk[rg][3], tap[cg][3]), hmul(kk[rg][2], tap[cg][2])), hmul(kk[rg][1], tap[cg][1])), hmul(kk[rg][0], tap[cg][0])), vv[rg]);
#pragma unroll
                for (int rg = 0; rg < 4; rg++) st_async(dst + (rg & 1) * 512 + (rg >> 1) * 16, vv[rg], xbar);
              }
            }
          }
          if (ci + 6 < 16 && elect_one()) {
            mbar_expect(sbar + 8 * b, 2304 + 2048);
            tma2d(stg + bo, &P.tmK, 16 * cl, 1024 * rank + 64 * (ci + 6) - 8, sbar + 8 * b);
            tma2d(stg + bo + 2304, &P.tmV, 16 * cl, 1024 * rank + 64 * (ci + 6), sbar + 8 * b);
            if (ci >= 0 && ci < 8) pf_l2(P.h + (blockIdx.x * 8 + ci) * 2048, 4096);
          }
          b ^= 1;
        }
      }
      if (lane == 0) STAMP(3, 3 + hw);
      asm volatile("bar.sync 4, 96;" ::: "memory");
      if (elect_one()) {
        if (hw == 0) { mbar_expect(BAR(B_XT), 10240); bulk_ld(sb + OFF_F2F, c_img, 10240, BAR(B_XT)); }
#pragma unroll 1
        for (int b = 0; b < 2; b++) {
          mbar_expect(sbar + 8 * b, 2048);
          tma3d(stg + b * 2048, &P.tmQ, 16 * cl, 64 * rank, 2 * (hw + 3 * b), sbar + 8 * b);
        }
      }
      mbar_wait(BAR(B_PKFREE), 0);
      if (hw == 0 && lane == 0) STAMP(3, 19);
      if (PD1) __nanosleep(PD1);
      {
        const int pi = hw < 2 ? 64 * mb + 32 * hw + lane : 512 + 2 * mb + (lane & 1);
        uint4 f[8];
        int n = 0;
        uint32_t bad;
        do {
#pragma unroll
          for (int p = 0; p < 8; p++) f[p] = ld_rlx4(&g_part[hp][p][4 * pi]);
          bad = stale8(f, tag);
          if (++n > SPIN_LIMIT) __trap();
        } while (__any_sync(~0u, bad & 1));
        float s0 = 0.f, s1 = 0.f, s2 = 0.f, s3 = 0.f;
#pragma unroll
        for (int p = 0; p < 8; p++) { s0 += __uint_as_float(f[p].x); s1 += __uint_as_float(f[p].y); s2 += __uint_as_float(f[p].z); s3 += __uint_as_float(f[p].w); }
        if (hw < 2 || lane < 2) st_tag4(&g_kv[hp][4 * pi], s0, s1, s2, s3, tag);
      }
      if (lane == 0 && hw == 0) STAMP(3, 8);
      if (hw == 2) {
        mbar_wait(BAR(B_ODONE), 0);
        if (lane < 2) {
          asm volatile("fence.acq_rel.gpu;" ::: "memory");
          asm volatile("red.relaxed.gpu.global.add.u32 [%0], 1;" ::"l"(&g_ocnt[(2 * mb + lane) * 32]) : "memory");
        }
        if (lane == 0) STAMP(3, 7);
        __syncwarp();
      } else {
        if (PD2) __nanosleep(PD2);
        const int t = hw * 32 + lane;
        uint4 f[8];
        uint4 zp;
        uint32_t bad;
        int n = 0;
        do {
          zp = ld_rlx4(&g_kv[hp][2048 + (t & 48) + 2 * (lane & 6)]);
#pragma unroll
          for (int p = 0; p < 8; p++) f[p] = ld_rlx4(&g_kv[hp][4 * ((p & 3) * 128 + (p >> 2) * 64 + t)]);
          bad = stale8(f, tag) | (zp.x ^ tag);
          if (++n > SPIN_LIMIT) __trap();
        } while (__any_sync(~0u, bad & 1));
#define PK2U(a, b) pk2(__uint_as_float(a), __uint_as_float(b))
#pragma unroll
        for (int hh = 0; hh < 2; hh++) {
          const uint4* ff = &f[4 * hh];
          uint8_t* dst = smem + OFF_KVB + hh * 2560 + q * 512 + (16 * hw + g) * 16;
          *(uint4*)dst = make_uint4(PK2U(ff[0].x, ff[0].y), PK2U(ff[1].x, ff[1].y), PK2U(ff[2].x, ff[2].y), PK2U(ff[3].x, ff[3].y));
          *(uint4*)(dst + 128) = make_uint4(PK2U(ff[0].z, ff[0].w), PK2U(ff[1].z, ff[1].w), PK2U(ff[2].z, ff[2].w), PK2U(ff[3].z, ff[3].w));
        }
        const uint32_t zf = (lane & 1) ? ((lane & 8) ? zp.w : zp.z) : ((lane & 8) ? zp.y : zp.x);
        const uint32_t zz = PK2U(zf, zf);
        *(uint4*)(smem + OFF_KVB + hw * 2560 + 2048 + lane * 16) = make_uint4(zz, zz, zz, zz);
        fence_async();
        __syncwarp();
        if (lane == 0) { mbar_arrive(BAR(B_KV)); if (hw == 0) STAMP(3, 9); }
      }
      mbar_wait(BAR(B_Y), 0);
      {
        const float2 sc0 = *(const float2*)(smem + OFF_SCALE + 8 * q), sc1 = *(const float2*)(smem + OFF_SCALE + 32 + 8 * q);
        const uint32_t yl = sb + OFF_XT + (lane & 7) * XT_STRIDE + (lane >> 3) * 16;
        int phs = ph, b = 0;
#pragma unroll 1
        for (int ci = hw; ci < 16; ci += 3) {
          const uint32_t qb = stg + b * 2048;
          mbar_wait(sbar + 8 * b, (phs >> b) & 1);
          phs ^= 1 << b;
#pragma unroll 1
          for (int nl = 0; nl < 2; nl++)
#pragma unroll
            for (int cg = 0; cg < 2; cg++) {
              uint32_t yy[4], qq[4];
              const uint32_t qa = ((qb + lane * 32 + ((lane & 4) << 2)) ^ (cg * 16)) + nl * 1024;
              ldsm4t(yy, yl + cg * 2048 + (2 * ci + nl) * 64);
              ldsm4(qq, qa);
              const float2 sc = cg ? sc1 : sc0;
#pragma unroll
              for (int m = 0; m < 4; m++) {
                const float2 f = __half22float2(*(const __half2*)&yy[m]);
                qq[m] = hmul(qq[m], pk2(f.x * sc.x, f.y * sc.y));
              }
              stsm4(qa, qq[0], qq[1], qq[2], qq[3]);
            }
          fence_async();
          __syncwarp();
          if (elect_one()) {
            tma3d_st(&P.tmOA, qb, 16 * cl, 64 * rank + 32 * (ci >> 3), 2 * (ci & 7));
            asm volatile("cp.async.bulk.commit_group;\ncp.async.bulk.wait_group.read 0;" ::: "memory");
            if (ci + 6 < 16) {
              mbar_expect(sbar + 8 * b, 2048);
              tma3d(qb, &P.tmQ, 16 * cl, 64 * rank + 32 * ((ci + 6) >> 3), 2 * ((ci + 6) & 7), sbar + 8 * b);
            }
          }
          b ^= 1;
        }
      }
      if (lane == 0) STAMP(3, 10 + hw);
    }
  }
}

typedef CUresult (*EncodeFn)(CUtensorMap*, CUtensorMapDataType, cuuint32_t, void*, const cuuint64_t*, const cuuint64_t*,
                             const cuuint32_t*, const cuuint32_t*, CUtensorMapInterleave, CUtensorMapSwizzle,
                             CUtensorMapL2promotion, CUtensorMapFloatOOBfill);

static void enc(EncodeFn fn, CUtensorMap* m, const void* p, int rank, const cuuint64_t* dims, const cuuint64_t* strides,
                const cuuint32_t* box, CUtensorMapSwizzle swz, CUtensorMapL2promotion promo) {
  cuuint32_t es[3] = {1, 1, 1};
  fn(m, CU_TENSOR_MAP_DATA_TYPE_BFLOAT16, rank, (void*)p, dims, strides, box, es, CU_TENSOR_MAP_INTERLEAVE_NONE, swz, promo,
     CU_TENSOR_MAP_FLOAT_OOB_FILL_NONE);
}

extern "C" void kernel_launch(void* const* d_in, const int* in_sizes, int n_in, void* d_out, int out_size) {
  void* fp = nullptr;
  cudaDriverEntryPointQueryResult qr;
  cudaGetDriverEntryPoint("cuTensorMapEncodeTiled", &fp, cudaEnableDefault, &qr);
  EncodeFn fn = (EncodeFn)fp;
  Params P;
  P.shift_k = (const __nv_bfloat16*)d_in[3]; P.h = (const __nv_bfloat16*)d_in[4]; P.D = (const __nv_bfloat16*)d_in[5];
  P.x = (const __nv_bfloat16*)d_in[6]; P.w = (const __nv_bfloat16*)d_in[7]; P.wo = (const __nv_bfloat16*)d_in[8];
  const CUtensorMapSwizzle S128 = CU_TENSOR_MAP_SWIZZLE_128B, S32 = CU_TENSOR_MAP_SWIZZLE_32B;
  const CUtensorMapL2promotion P0 = CU_TENSOR_MAP_L2_PROMOTION_NONE, P128 = CU_TENSOR_MAP_L2_PROMOTION_L2_128B;
  { cuuint64_t d[2] = {1024, 2048}, s[1] = {2048}; cuuint32_t b[2] = {64, 128}; enc(fn, &P.tmX, d_in[6], 2, d, s, b, S128, P128); }
  { cuuint64_t d[3] = {1024, 1024, 3}, s[2] = {6144, 2048}; cuuint32_t b[3] = {64, 64, 3}; enc(fn, &P.tmW, d_in[7], 3, d, s, b, S128, P128); }
  { cuuint64_t d[3] = {64, 1024, 16}, s[2] = {2048, 128}; cuuint32_t b[3] = {64, 64, 2}; enc(fn, &P.tmWo, d_in[8], 3, d, s, b, S128, P128); }
  { cuuint64_t d[2] = {1024, 2048}, s[1] = {2048}; cuuint32_t b[2] = {16, 72}; enc(fn, &P.tmK, d_in[1], 2, d, s, b, S32, PKV); }
  { cuuint64_t d[2] = {1024, 2048}, s[1] = {2048}; cuuint32_t b[2] = {16, 64}; enc(fn, &P.tmV, d_in[2], 2, d, s, b, S32, PKV); }
  { cuuint64_t d[3] = {1024, 128, 16}, s[2] = {32768, 2048}; cuuint32_t b[3] = {16, 32, 2}; enc(fn, &P.tmQ, d_in[0], 3, d, s, b, S32, PKV); }
  { cuuint64_t d[3] = {1024, 128, 16}, s[2] = {65536, 4096}; cuuint32_t b[3] = {16, 32, 2}; enc(fn, &P.tmOA, d_out, 3, d, s, b, S32, P0); }
  { cuuint64_t d[2] = {2048, 2048}, s[1] = {4096}; cuuint32_t b[2] = {64, 64}; enc(fn, &P.tmOB, d_out, 2, d, s, b, S128, P0); }
  cudaFuncSetAttribute(fused_kernel, cudaFuncAttributeMaxDynamicSharedMemorySize, SMEM_TOTAL);
  fused_kernel<<<128, 384, SMEM_TOTAL>>>(P);
}
```

```cpp
#include <cuda_runtime.h>
#include <cuda_bf16.h>
#include <cuda_fp16.h>
#include <cuda.h>
#include <stdint.h>

template<int TA, int TB, int SA=1> __device__ __forceinline__ void wgmma_ss_n192(float (&d)[96], uint64_t da, uint64_t db, int scale_d) {
  asm volatile("{\n.reg .pred p;\nsetp.ne.b32 p, %98, 0;\n"
    "wgmma.mma_async.sync.aligned.m64n192k16.f32.bf16.bf16 {%0, %1, %2, %3, %4, %5, %6, %7, %8, %9, %10, %11, %12, %13, %14, %15, %16, %17, %18, %19, %20, %21, %22, %23, %24, %25, %26, %27, %28, %29, %30, %31, %32, %33, %34, %35, %36, %37, %38, %39, %40, %41, %42, %43, %44, %45, %46, %47, %48, %49, %50, %51, %52, %53, %54, %55, %56, %57, %58, %59, %60, %61, %62, %63, %64, %65, %66, %67, %68, %69, %70, %71, %72, %73, %74, %75, %76, %77, %78, %79, %80, %81, %82, %83, %84, %85, %86, %87, %88, %89, %90, %91, %92, %93, %94, %95}, %96, %97, p, %101, 1, %99, %100;\n}\n"
    : "+f"(d[0]), "+f"(d[1]), "+f"(d[2]), "+f"(d[3]), "+f"(d[4]), "+f"(d[5]), "+f"(d[6]), "+f"(d[7]), "+f"(d[8]), "+f"(d[9]), "+f"(d[10]), "+f"(d[11]), "+f"(d[12]), "+f"(d[13]), "+f"(d[14]), "+f"(d[15]), "+f"(d[16]), "+f"(d[17]), "+f"(d[18]), "+f"(d[19]), "+f"(d[20]), "+f"(d[21]), "+f"(d[22]), "+f"(d[23]), "+f"(d[24]), "+f"(d[25]), "+f"(d[26]), "+f"(d[27]), "+f"(d[28]), "+f"(d[29]), "+f"(d[30]), "+f"(d[31]), "+f"(d[32]), "+f"(d[33]), "+f"(d[34]), "+f"(d[35]), "+f"(d[36]), "+f"(d[37]), "+f"(d[38]), "+f"(d[39]), "+f"(d[40]), "+f"(d[41]), "+f"(d[42]), "+f"(d[43]), "+f"(d[44]), "+f"(d[45]), "+f"(d[46]), "+f"(d[47]), "+f"(d[48]), "+f"(d[49]), "+f"(d[50]), "+f"(d[51]), "+f"(d[52]), "+f"(d[53]), "+f"(d[54]), "+f"(d[55]), "+f"(d[56]), "+f"(d[57]), "+f"(d[58]), "+f"(d[59]), "+f"(d[60]), "+f"(d[61]), "+f"(d[62]), "+f"(d[63]), "+f"(d[64]), "+f"(d[65]), "+f"(d[66]), "+f"(d[67]), "+f"(d[68]), "+f"(d[69]), "+f"(d[70]), "+f"(d[71]), "+f"(d[72]), "+f"(d[73]), "+f"(d[74]), "+f"(d[75]), "+f"(d[76]), "+f"(d[77]), "+f"(d[78]), "+f"(d[79]), "+f"(d[80]), "+f"(d[81]), "+f"(d[82]), "+f"(d[83]), "+f"(d[84]), "+f"(d[85]), "+f"(d[86]), "+f"(d[87]), "+f"(d[88]), "+f"(d[89]), "+f"(d[90]), "+f"(d[91]), "+f"(d[92]), "+f"(d[93]), "+f"(d[94]), "+f"(d[95])
    : "l"(da), "l"(db), "r"(scale_d), "n"(TA), "n"(TB), "n"(SA));
}
template<int TA, int TB, int SA=1> __device__ __forceinline__ void wgmma_ss_n128(float (&d)[64], uint64_t da, uint64_t db, int scale_d) {
  asm volatile("{\n.reg .pred p;\nsetp.ne.b32 p, %66, 0;\n"
    "wgmma.mma_async.sync.aligned.m64n128k16.f32.bf16.bf16 {%0, %1, %2, %3, %4, %5, %6, %7, %8, %9, %10, %11, %12, %13, %14, %15, %16, %17, %18, %19, %20, %21, %22, %23, %24, %25, %26, %27, %28, %29, %30, %31, %32, %33, %34, %35, %36, %37, %38, %39, %40, %41, %42, %43, %44, %45, %46, %47, %48, %49, %50, %51, %52, %53, %54, %55, %56, %57, %58, %59, %60, %61, %62, %63}, %64, %65, p, %69, 1, %67, %68;\n}\n"
    : "+f"(d[0]), "+f"(d[1]), "+f"(d[2]), "+f"(d[3]), "+f"(d[4]), "+f"(d[5]), "+f"(d[6]), "+f"(d[7]), "+f"(d[8]), "+f"(d[9]), "+f"(d[10]), "+f"(d[11]), "+f"(d[12]), "+f"(d[13]), "+f"(d[14]), "+f"(d[15]), "+f"(d[16]), "+f"(d[17]), "+f"(d[18]), "+f"(d[19]), "+f"(d[20]), "+f"(d[21]), "+f"(d[22]), "+f"(d[23]), "+f"(d[24]), "+f"(d[25]), "+f"(d[26]), "+f"(d[27]), "+f"(d[28]), "+f"(d[29]), "+f"(d[30]), "+f"(d[31]), "+f"(d[32]), "+f"(d[33]), "+f"(d[34]), "+f"(d[35]), "+f"(d[36]), "+f"(d[37]), "+f"(d[38]), "+f"(d[39]), "+f"(d[40]), "+f"(d[41]), "+f"(d[42]), "+f"(d[43]), "+f"(d[44]), "+f"(d[45]), "+f"(d[46]), "+f"(d[47]), "+f"(d[48]), "+f"(d[49]), "+f"(d[50]), "+f"(d[51]), "+f"(d[52]), "+f"(d[53]), "+f"(d[54]), "+f"(d[55]), "+f"(d[56]), "+f"(d[57]), "+f"(d[58]), "+f"(d[59]), "+f"(d[60]), "+f"(d[61]), "+f"(d[62]), "+f"(d[63])
    : "l"(da), "l"(db), "r"(scale_d), "n"(TA), "n"(TB), "n"(SA));
}
template<int TA, int TB, int SA=1> __device__ __forceinline__ void wgmma_ss_n72(float (&d)[36], uint64_t da, uint64_t db, int scale_d) {
  asm volatile("{\n.reg .pred p;\nsetp.ne.b32 p, %38, 0;\n"
    "wgmma.mma_async.sync.aligned.m64n72k16.f32.bf16.bf16 {%0, %1, %2, %3, %4, %5, %6, %7, %8, %9, %10, %11, %12, %13, %14, %15, %16, %17, %18, %19, %20, %21, %22, %23, %24, %25, %26, %27, %28, %29, %30, %31, %32, %33, %34, %35}, %36, %37, p, %41, 1, %39, %40;\n}\n"
    : "+f"(d[0]), "+f"(d[1]), "+f"(d[2]), "+f"(d[3]), "+f"(d[4]), "+f"(d[5]), "+f"(d[6]), "+f"(d[7]), "+f"(d[8]), "+f"(d[9]), "+f"(d[10]), "+f"(d[11]), "+f"(d[12]), "+f"(d[13]), "+f"(d[14]), "+f"(d[15]), "+f"(d[16]), "+f"(d[17]), "+f"(d[18]), "+f"(d[19]), "+f"(d[20]), "+f"(d[21]), "+f"(d[22]), "+f"(d[23]), "+f"(d[24]), "+f"(d[25]), "+f"(d[26]), "+f"(d[27]), "+f"(d[28]), "+f"(d[29]), "+f"(d[30]), "+f"(d[31]), "+f"(d[32]), "+f"(d[33]), "+f"(d[34]), "+f"(d[35])
    : "l"(da), "l"(db), "r"(scale_d), "n"(TA), "n"(TB), "n"(SA));
}
template<int TB, int SA=1> __device__ __forceinline__ void wgmma_rs_n40(float (&d)[20], uint32_t a0, uint32_t a1, uint32_t a2, uint32_t a3, uint64_t db, int scale_d) {
  asm volatile("{\n.reg .pred p;\nsetp.ne.b32 p, %25, 0;\n"
    "wgmma.mma_async.sync.aligned.m64n40k16.f32.bf16.bf16 {%0, %1, %2, %3, %4, %5, %6, %7, %8, %9, %10, %11, %12, %13, %14, %15, %16, %17, %18, %19}, {%20, %21, %22, %23}, %24, p, %27, 1, %26;\n}\n"
    : "+f"(d[0]), "+f"(d[1]), "+f"(d[2]), "+f"(d[3]), "+f"(d[4]), "+f"(d[5]), "+f"(d[6]), "+f"(d[7]), "+f"(d[8]), "+f"(d[9]), "+f"(d[10]), "+f"(d[11]), "+f"(d[12]), "+f"(d[13]), "+f"(d[14]), "+f"(d[15]), "+f"(d[16]), "+f"(d[17]), "+f"(d[18]), "+f"(d[19])
    : "r"(a0), "r"(a1), "r"(a2), "r"(a3), "l"(db), "r"(scale_d), "n"(TB), "n"(SA));
}
template<int TB> __device__ __forceinline__ void wgmma_hrs_n64(uint32_t (&d)[16], uint32_t a0, uint32_t a1, uint32_t a2, uint32_t a3, uint64_t db, int scale_d) {
  asm volatile("{\n.reg .pred p;\nsetp.ne.b32 p, %21, 0;\n"
    "wgmma.mma_async.sync.aligned.m64n64k16.f16.f16.f16 {%0, %1, %2, %3, %4, %5, %6, %7, %8, %9, %10, %11, %12, %13, %14, %15}, {%16, %17, %18, %19}, %20, p, 1, 1, %22;\n}\n"
    : "+r"(d[0]), "+r"(d[1]), "+r"(d[2]), "+r"(d[3]), "+r"(d[4]), "+r"(d[5]), "+r"(d[6]), "+r"(d[7]), "+r"(d[8]), "+r"(d[9]), "+r"(d[10]), "+r"(d[11]), "+r"(d[12]), "+r"(d[13]), "+r"(d[14]), "+r"(d[15])
    : "r"(a0), "r"(a1), "r"(a2), "r"(a3), "l"(db), "r"(scale_d), "n"(TB));
}
template<int TB> __device__ __forceinline__ void wgmma_hrs_n32(uint32_t (&d)[8], uint32_t a0, uint32_t a1, uint32_t a2, uint32_t a3, uint64_t db, int scale_d) {
  asm volatile("{\n.reg .pred p;\nsetp.ne.b32 p, %13, 0;\n"
    "wgmma.mma_async.sync.aligned.m64n32k16.f16.f16.f16 {%0, %1, %2, %3, %4, %5, %6, %7}, {%8, %9, %10, %11}, %12, p, 1, 1, %14;\n}\n"
    : "+r"(d[0]), "+r"(d[1]), "+r"(d[2]), "+r"(d[3]), "+r"(d[4]), "+r"(d[5]), "+r"(d[6]), "+r"(d[7])
    : "r"(a0), "r"(a1), "r"(a2), "r"(a3), "l"(db), "r"(scale_d), "n"(TB));
}

__device__ __align__(128) const uint32_t c_thr[1536] = {
  0x33fb33ff,0xa49c9de4,0x33273352,0xaf2cae76,0x33e233f1,0xa96ca7bd,0x32c432f7,0xb045afdd,0x33b733cf,0xac3eaaf7,0x3250328c,0xb0eab099,
  0x3378339a,0xadbcacff,0x31cd3211,0xb182b137,0x33d033fb,0xaadea46a,0x299e2d17,0xb3e0b396,0x32fb337a,0xafd2adb1,0xa78b1f76,0xb3f2b3ff,
  0x318b3254,0xb1c5b0e5,0xae6bac32,0xb354b3b8,0x2f4230a3,0xb321b285,0xb133b040,0xb215b2c7,0x337c33f2,0xada5a759,0xb179afc8,0xb1d6b2fe,
  0x31463293,0xb204b08e,0xb394b2ba,0xad23b055,0x2b402f4e,0xb3cbb31e,0xb3e4b3f9,0x293ba533,0xac269c52,0xb3bab400,0xb258b357,0x30e02e5f,
  0x330133e5,0xafbda922,0xb3f3b3c9,0x2727ab59,0x2deb314a,0xb36fb200,0xb194b32f,0x31bc2f0a,0xacdb2084,0xb39fb3ff,0xa565aea4,0x33f93347,
  0xb2b6b0db,0xb05ab25c,0x30892c1a,0x329733bc,0x326033d4,0xb0d6aa94,0xb00ab29b,0x32e83084,0x20e82f64,0xb3feb318,0x2d8da597,0x338133f8,
  0xb1fcae48,0xb14fb35c,0x339031b8,0x2d3a3199,0xb3e6b3ae,0x2909ac7b,0x32d133f4,0xb030a6f5,0x319d33bf,0xb1b3ac02,0x2e3ca874,0x335e33ec,
  0xacc32b89,0xb3a3b3c6,0x33f83276,0x25c930b7,0xb3dcb1f8,0xaa01b154,0x30653335,0xb2b0aef4,0xb107b383,0x32392d81,0xafa6214d,0xb307b3fe,
  0x30bc33a5,0xb273acb7,0x33c5311b,0x2ba23229,0xb0cc94b6,0xb267b400,0x30153360,0xb2e1ae31,0xb385b3ab,0x2d76ac93,0xb166a691,0xb1e7b3f5,
  0x22deb06a,0x33fd32ac,0xb337b3da,0x2ee8aa19,0x2f853387,0xb310ad6a,0x322d33fe,0xb1162216,0xb2a9abd3,0xb06fb3c2,0xb07428a6,0xb2a5b3ea,
  0xb111b3e9,0x323128be,0xb30db3c3,0x2f90abba,0x31aa227a,0x31a633fd,0x2e25ad5e,0x33633389,0x2d6a3365,0xb387ae1a,0xa21631aa,0xb3feb1a6,
  0xb3c2af85,0xabd3b310,0xb3eab22d,0x28a6b116,0xa8beb2a9,0x33e9306f,0x2bbab074,0x33c332a5,0x33fd3111,0x227a3231,0x3389330d,0xad5e2f90,
  0x2a63333f,0xb3d7aec6,0xb2a2a1b1,0xb07ab3fe,0xb3f7b158,0x25fbb1f4,0xacb7b38b,0x33a52d52,0x2e0eb025,0x336832d8,0x340030bc,0x14b63273,
  0x323533c0,0xb10c2beb,0xac9330cc,0xb3abb267,0x23433316,0xb3fdaf6f,0xb38eb225,0x2d46b11f,0xb342b29e,0x2ebbb07f,0x31e3aa7c,0x316b33d6,
  0x3264a6c3,0x30d133f5,0x2c0233ac,0xb3bfac87,0x28f0336a,0xb3e7ae02,0xb3c6b19d,0x2b89b1b3,0xa59732e8,0xb3f8b00a,0xaccfb3ed,0x33a1285b,
  0xb1b8b381,0x3199ad8d,0x336c31df,0xadf73170,0x33f42d3a,0x26f53390,0xb30423a7,0xafb2b3fc,0xb05f3030,0xb2b3b2d1,0x29e8b27a,0x33dd30b2,
  0xab5932b6,0xb3c9b05a,0x30adb089,0x327e3297,0xaf0ab3f3,0x332fa727,0x240633b0,0xb3fcac6f,0x33473194,0xaea431bc,0xb174b359,0x31daae54,
  0xb3bca565,0xac1ab3f9,0x33ee2f59,0xa842331b,0xaddf3281,0xb371b0a8,0x34002b40,0x1c5233cb,0xa759b3ef,0x33f22829,0xb2fe2c26,0xafc8b3ba,
  0x308e337c,0xb2932da5,0x3055b179,0x32ba31d6,0xb31eb146,0x2f4eb204,0xa5333394,0xb3f9ad23,0xaff33249,0xb2f1b0f3,0x30e532fb,0xb2542fd2,
  0x2b28b373,0x33cc2dd4,0xb285b18b,0x30a3b1c5,0x246a33fa,0xb3fba500,0x33962f42,0xad173321,0xadb1b3d0,0x337aaade,0xb3ffa99e,0x1f76b3e0,
  0xb0ee320d,0xb24db13c,0xac4b3398,0xb3b5ad0b,0x304ab289,0x32c1309e,0x2985b3ce,0x33e12b0f,0xaf3732f4,0xb324afe8,0xa4ce33f0,0xb3faa7ef,
  0x2dc8b34f,0x33762e82,0x9de4b3ff,0x33ff1ead,0xb1c931cd,0xb186b182,0xb3762e82,0xadc8b34f,0x324db13c,0x30ee320d,0x33b5ad0b,0x2c4b3398,
  0xb2c1309e,0xb04ab289,0xb3e12b0f,0xa985b3ce,0x3324afe8,0x2f3732f4,0x33faa7ef,0x24ce33f0,0xb285318b,0xb0a3b1c5,0xb2c7ae6b,0x3040b354,
  0x3396af42,0x2d173321,0x31413133,0xb2093215,0xb3ff299e,0x9f76b3e0,0xae8db2bd,0x334cb050,0x33b8278b,0xac3233f2,0x281033b3,0xb3ef2c57,
  0xb31e3146,0xaf4eb204,0xa533b394,0x33f9ad23,0x3400ab40,0x9c5233cb,0xae5f33e4,0xb357a93b,0xb2feac26,0x2fc8b3ba,0x3245b258,0x30f830e0,
  0x30553179,0xb2ba31d6,0xb3df2e99,0xa9b6b34a,0xb39230fd,0xad2fb241,0x3200b301,0x314a2fbd,0x337f1b11,0xad993400,0xb3ff2deb,0xa084b36f,
  0xb005b129,0x32ebb21d,0x325c2cdb,0xb0db339f,0xa92233de,0xb3e529cf,0xab59b2b6,0x33c9b05a,0xb3dd30b2,0xa9e8b27a,0x33d4ab71,0xaa9433c8,
  0x32212c0e,0xb12433bd,0xaf64b0d6,0x3318b260,0x197fb345,0x3400aeaf,0xae4833fe,0xb35c20e8,0xb23d3332,0xb102aeff,0x33aeb14f,0x2c7b31fc,
  0xb3fe3065,0xa14db2b0,0x2ebb307f,0xb342329e,0x300f2fa6,0xb2e53307,0x30d1b3f5,0x326426c3,0x302ab400,0x32d517db,0xb3e72e02,0x28f0b36a,
  0xb3fd2f6f,0x2343b316,0x2d46311f,0xb38e3225,0xb3f53015,0x2691b2e1,0xaf9b33eb,0xb30a288d,0x2a193166,0xb3da31e7,0x33d7aec6,0xaa63333f,
  0x3313b337,0x2f7a2ee8,0xa5fbb1f4,0x33f7b158,0xb1a1a8d7,0x31afb3e8,0xb36832d8,0xae0eb025,0xb3c22f85,0x2bd3b310,0xb3ea322d,0xa8a6b116,
  0xa8be32a9,0xb3e9306f,0x2bba3074,0xb3c332a5,0x33fdb111,0xa27a3231,0x3389b30d,0x2d5e2f90,0xa216b1aa,0x33feb1a6,0xaed2ae25,0x333db363,
  0xb3652edd,0x2e1ab33a,0xb1aa227a,0x31a6b3fd,0xaf853387,0xb3102d6a,0xb22d33fe,0xb116a216,0x32a9abd3,0xb06f33c2,0x307428a6,0xb2a533ea,
  0x3111b3e9,0x3231a8be,0x330db3c3,0x2f902bba,0xb2e12e31,0x3015b360,0x288db1a1,0x33ebb1af,0xb1e733f5,0xb1662691,0xb33f2f9b,0x2ec6b30a,
  0x2ee82a19,0xb33733da,0xb15833d7,0xb1f42a63,0x33e8b313,0x28d72f7a,0x302525fb,0xb2d833f7,0xb2392d81,0x3107b383,0x3307b3fe,0x2fa6214d,
  0xb35e33ec,0xae3ca874,0x97dbb00f,0x3400b2e5,0xa5c930b7,0xb3f83276,0xb316302a,0x2f6fb2d5,0x32b0aef4,0xb0653335,0xb29e33fd,0xb07f2343,
  0xb1702ccf,0x31dfb3a1,0x3345b124,0xaeaf3221,0xb3fc336c,0xa3a7adf7,0x3332b400,0x2eff997f,0xb0b23304,0xb27a2fb2,0x2b71b102,0x33c8b23d,
  0x2c0e29e8,0xb3bd33dd,0xb0d62a94,0x3260b3d4,0xb0892c1a,0x3297b3bc,0x2aad2842,0xb3d333ee,0xb3b0327e,0x2c6fb0ad,0x3241b035,0xb0fd32ce,
  0xb35933fc,0xae542406,0x3400b392,0x1b112d2f,0xaf5931da,0xb31b3174,0x321db37f,0x3129ad99,0xaf152ac6,0x332cb3d2,0xb1463293,0xb204308e,
  0xb281312e,0x30a8b219,0xab402f4e,0xb3cb331e,0xb3ef3371,0x2829addf,0x2c269c52,0xb3ba3400,0xb37c33f2,0xada52759,0x3179afc8,0xb1d632fe,
  0xacf32953,0x339cb3e3,0xb3fa33cc,0x2500ab28,0xb0942f21,0x3290b32a,0xb3d033fb,0xaade246a,0xb249317d,0x30f3b1d2,0xb2fb337a,0xafd22db1,
  0xb37332f1,0x2dd4aff3,0xb18b3254,0xb1c530e5,0xa96c27bd,0x33e2b3f1,0xb0452fdd,0x32c4b2f7,0xac3e2af7,0x33b7b3cf,0xb0ea3099,0x3250b28c,
  0xadbc2cff,0x3378b39a,0xb1823137,0x31cdb211,0xaf2c2e76,0x3327b352,0xb20d31c9,0x313cb186,0x313c3186,0xb20db1c9,0x2d0b2dc8,0xb398b376,
  0x309e30ee,0xb289b24d,0x2b0f2c4b,0xb3ceb3b5,0x2fe8304a,0xb2f4b2c1,0x27ef2985,0xb3f0b3e1,0x2e822f37,0xb34fb324,0x1ead24ce,0xb3ffb3fa,
  0xb2bdb209,0xb050b141,0xb290b32a,0x30942f21,0xb3b3b34c,0xac57ae8d,0xb0f3b1d2,0x3249317d,0xb400b3ef,0x1d1ba810,0xadd4aff3,0x337332f1,
  0xb39cb3e3,0x2cf32953,0xa500ab28,0x33fa33cc,0xae99b0f8,0x334a3245,0x33ff33b2,0x201f2c63,0x2438a9b6,0x33fc33df,0x332c33d2,0xaf15aac6,
  0x303a2ce7,0x32cb339e,0x30a83219,0xb281b12e,0x32ee31c0,0x2ffe3190,0x28292ddf,0xb3efb371,0x33b0327e,0x2c6f30ad,0xb241b035,0xb0fdb2ce,
  0x335933fc,0xae54a406,0xb400b392,0x1b11ad2f,0x2f5931da,0xb31bb174,0xb21db37f,0x31292d99,0xaaad2842,0xb3d3b3ee,0xa9cfb005,0x33de32eb,
  0x285b305f,0xb3edb2b3,0x2c0ea9e8,0x33bd33dd,0xb170accf,0xb1dfb3a1,0x33453124,0x2eaf3221,0xb3fcb36c,0x23a7adf7,0x33323400,0xaeff997f,
  0xb0b2b304,0x327a2fb2,0x2b713102,0xb3c8b23d,0xb400b2e5,0x17dbb00f,0x2e023264,0xb36ab0d1,0xaf6fb2d5,0x3316302a,0xb11fa8f0,0xb225b3e7,
  0x307f2343,0x329e33fd,0xb3d6b38e,0x2a7cad46,0x33f53342,0xa6c32ebb,0xac87b1e3,0x33ac316b,0x28d7af7a,0x33e83313,0xb2d8b3f7,0x3025a5fb,
  0x33eb31af,0x288d31a1,0x2bebae0e,0x33c03368,0x2ec6330a,0xb33faf9b,0x33fe3235,0x21b1310c,0xb1f4aa63,0xb158b3d7,0x2d5232a2,0xb38bb07a,
  0x33a7333d,0xacab2ed2,0x33f63162,0x262d31eb,0xaa4b301a,0xb3d8b2de,0x2a32326b,0xb3d9b0c7,0xb3f6b26f,0x265fb0c1,0xb3a9b020,0xac9fb2db,
  0x0e48b15d,0x340031f0,0xae1ab33a,0x33652edd,0xaed22e25,0xb33db363,0xb1eb0e48,0xb162b400,0xb2deb3a7,0x301aacab,0xb0c7b3f6,0x326b262d,
  0x30c1aa4b,0x326f33d8,0x32db2a32,0x302033d9,0x31f033f6,0xb15d265f,0x2edd33a9,0xb33aac9f,0xb2acb385,0x306aad76,0x2a19b166,0x33da31e7,
  0x3229a2de,0x311b33fd,0x33133337,0xaf7a2ee8,0x2e3133c5,0xb360aba2,0xb1a128d7,0xb1afb3e8,0xb3f5b015,0xa691b2e1,0xaf9bb3eb,0x330a288d,
  0x3154acc3,0x31f833a3,0x2ef433f8,0xb335a5c9,0x2d8133dc,0xb383aa01,0xb3feb065,0x214db2b0,0xb3ecb107,0x2874b239,0x300fafa6,0x32e53307,
  0x30b7ae3c,0x3276335e,0x302a3400,0xb2d517db,0x312433bd,0xb2212c0e,0xb318b260,0x2f64b0d6,0xb400aeaf,0x997fb345,0x335c20e8,0x2e4833fe,
  0x3102aeff,0x323d3332,0xac7b31fc,0xb3aeb14f,0x2a9433c8,0xb3d4ab71,0xb084b3e6,0x329ba909,0xb2ce2aad,0xb035b3d3,0x33e529cf,0x292233de,
  0x2d2fb241,0x339230fd,0xb14a2fbd,0xb200b301,0x2d993400,0xb37f1b11,0x2084b36f,0x33ff2deb,0xb2ebb21d,0x3005b129,0x30db339f,0xb25c2cdb,
  0xae5fb3e4,0x3357a93b,0xb190303a,0xb1c0b2cb,0x32453258,0xb0f830e0,0x2c63b2ee,0x33b22ffe,0xb3dfae99,0x29b6b34a,0x2ac633ff,0xb3d2a01f,
  0x339ea438,0x2ce733fc,0xb12eb32c,0x3219af15,0x33b8a78b,0x2c3233f2,0x2810b3b3,0x33ef2c57,0xb2c72e6b,0xb040b354,0x29533400,0xb3e31d1b,
  0x3141b133,0x32093215,0xaf21b39c,0x332aacf3,0xae8d32bd,0xb34cb050,0x317d3290,0xb1d23094,0x27bd33fb,0xb3f1249c,0x2fdd3327,0xb2f72f2c,
  0xaaf7b3e2,0x33cfa96c,0xb099b2c4,0x328cb045,0x2cff33b7,0xb39a2c3e,0x31373250,0xb21130ea,0xae76b378,0x3352adbc,0xb1c9b1cd,0x3186b182,
  0xb3ff1ead,0x1de4b3ff,0xb352adbc,0x2e76b378,0x33f1249c,0xa7bd33fb,0x32f72f2c,0xafdd3327,0xb3cfa96c,0x2af7b3e2,0xb28cb045,0x3099b2c4,
  0x339a2c3e,0xacff33b7,0x321130ea,0xb1373250,0x2953b400,0x33e31d1b,0x33ccadd4,0x2b283373,0xaf21339c,0xb32aacf3,0xb3fb2500,0x246ab3fa,
  0x317db290,0x31d23094,0x337a2ade,0xadb133d0,0xb2f130f3,0xaff3b249,0xb254afd2,0x30e5b2fb,0x339e2438,0xace733fc,0xb12e332c,0xb219af15,
  0xb190b03a,0x31c0b2cb,0x3371b0a8,0x2ddf3281,0x2c6332ee,0xb3b22ffe,0xb3f22829,0x2759b3ef,0x2ac6b3ff,0x33d2a01f,0x32932da5,0xb08e337c,
  0xaf0a33f3,0xb32fa727,0x2406b3b0,0x33fcac6f,0x3347b194,0x2ea431bc,0xb1743359,0xb1daae54,0xb3bc2565,0x2c1ab3f9,0x33eeaf59,0x2842331b,
  0x30ad3089,0xb27e3297,0xb2ceaaad,0x3035b3d3,0xb29ba909,0x3084b3e6,0x305f3030,0xb2b332d1,0x259732e8,0xb3f8300a,0x2ccfb3ed,0x33a1a85b,
  0x31b8b381,0x31992d8d,0xb36c31df,0xadf7b170,0xb3f42d3a,0x26f5b390,0x330423a7,0xafb233fc,0x316bb3d6,0x31e32a7c,0xb3832a01,0x2d81b3dc,
  0xb3bf2c87,0x2c02b3ac,0x28743239,0xb3ec3107,0x2b8931b3,0xb3c6319d,0x3276b35e,0x30b72e3c,0x31f8b3a3,0x31542cc3,0xb33525c9,0x2ef4b3f8,
  0x310c2beb,0xb23533c0,0x33abb267,0x2c9330cc,0x307ab3fe,0x32a2a1b1,0xb06aad76,0x32acb385,0xb3a52d52,0x2cb7b38b,0xb11b33fd,0xb229a2de,
  0x94b63273,0xb40030bc,0x3360aba2,0xae3133c5,0xb2de33a7,0xb01aacab,0xb0c733f6,0xb26b262d,0x30c12a4b,0xb26f33d8,0x32dbaa32,0xb02033d9,
  0x31f0b3f6,0x315d265f,0x2eddb3a9,0x333aac9f,0xb1eb8e48,0x3162b400,0xb3872e1a,0x2d6ab365,0xae25ad5e,0x3363b389,0x8e48b15d,0x3400b1f0,
  0xb3a7333d,0xacabaed2,0xb3f63162,0x262db1eb,0x2a4b301a,0xb3d832de,0xaa32326b,0xb3d930c7,0x33f6b26f,0x265f30c1,0x33a9b020,0xac9f32db,
  0x33c0b368,0x2beb2e0e,0x30cc94b6,0xb2673400,0x21b1b10c,0x33feb235,0x3385b3ab,0x2d762c93,0xb38b307a,0x2d52b2a2,0xa2deb06a,0x33fdb2ac,
  0xb0bc33a5,0xb2732cb7,0xb3c5311b,0x2ba2b229,0x26c32ebb,0xb3f53342,0xb3ac316b,0x2c87b1e3,0x336ab0d1,0xae023264,0xb19d33bf,0xb1b32c02,
  0x3225b3e7,0x311fa8f0,0x2cc32b89,0xb3a333c6,0xaa7cad46,0x33d6b38e,0x33dcb1f8,0xaa013154,0xb3fe3318,0x20e8af64,0x3381b3f8,0x2d8d2597,
  0xb14f335c,0xb1fc2e48,0x2d3ab199,0x3390b1b8,0x29092c7b,0xb3e633ae,0xb03026f5,0x32d1b3f4,0x32e8b084,0xb00a329b,0xb3ed32b3,0x285bb05f,
  0x29cfb005,0x33deb2eb,0xb05a325c,0xb2b630db,0xafbd2922,0x3301b3e5,0x27272b59,0xb3f333c9,0xb36f3200,0x2debb14a,0x31bcaf0a,0xb194332f,
  0xb39f33ff,0xacdba084,0x33f9b347,0xa5652ea4,0x3394b2ba,0xad233055,0xa438a9b6,0x33fcb3df,0x33e4b3f9,0x293b2533,0xb03a2ce7,0x32cbb39e,
  0x3258b357,0x30e0ae5f,0xb2ee31c0,0x2ffeb190,0x2e99b0f8,0x334ab245,0xb3ff33b2,0x201fac63,0xaf4230a3,0xb3213285,0x3133b040,0xb21532c7,
  0xa99e2d17,0xb3e03396,0x32bdb209,0xb0503141,0x278b1f76,0xb3f233ff,0x33b3b34c,0xac572e8d,0x2e6bac32,0xb35433b8,0x3400b3ef,0x1d1b2810,
  0xb289324d,0x309eb0ee,0xb3ce33b5,0x2b0fac4b,0xb2f432c1,0x2fe8b04a,0xb3f033e1,0x27efa985,0xb34f3324,0x2e82af37,0xb3ff33fa,0x1eada4ce,
  0xb3983376,0x2d0badc8,0xb3fb33ff,0xa49c1de4,0x351c35f6,0xac93a617,0xb8a3b93c,0x308d2a16,0x32f43448,0xb160afa5,0xb6a4b7fe,0x353a3389,
  0x2fa53160,0xb448b2f4,0xb389b53a,0x37fe36a4,0x26172c93,0xb5f6b51c,0xaa16b08d,0x393c38a3,0x34c3358c,0xac47a5b2,0xb85fb8f3,0x304229b1,
  0x327e33fd,0xb106af26,0xb63cb785,0x34e7330f,0x2f263106,0xb3fdb27e,0xb30fb4e7,0x3785363c,0x25b22c47,0xb58cb4c3,0xa9b1b042,0x38f3385f,
  0x346a3523,0xabf6a54d,0xb81ab8a8,0x2fef294d,0x3209336b,0xb0acaea7,0xb5d4b70a,0x34933294,0x2ea730ac,0xb36bb209,0xb294b493,0x370a35d4,
  0x254d2bf6,0xb523b46a,0xa94dafef,0x38a8381a,0x341334bc,0xab5fa4e9,0xb7a6b85a,0x2f5928e8,0x319432da,0xb052ae28,0xb56ab68d,0x343e3219,
  0x2e283052,0xb2dab194,0xb219b43e,0x368d356a,0x24e92b5f,0xb4bcb413,0xa8e8af59,0x385a37a6,0x33783456,0xaac8a484,0xb715b80a,0x2ec32884,
  0x3120324a,0xaff2ada9,0xb4ffb60e,0x33d3319e,0x2da92ff2,0xb24ab120,0xb19eb3d3,0x360e34ff,0x24842ac8,0xb456b378,0xa884aec3,0x380a3715,
  0x32cd33e3,0xaa31a420,0xb682b76f,0x2e2d281f,0x30ac31bb,0xaf3fad2a,0xb493b58d,0x33283122,0x2d2a2f3f,0xb1bbb0ac,0xb122b328,0x358d3493,
  0x24202a31,0xb3e3b2cd,0xa81fae2d,0x376f3682,0x3223331c,0xa999a376,0xb5ebb6c6,0x2d972776,0x3039312d,0xae8dacac,0xb426b50b,0x327c30a6,
  0x2cac2e8d,0xb12db039,0xb0a6b27c,0x350b3426,0x23762999,0xb31cb223,0xa776ad97,0x36c635eb,0x317a3257,0xa902a2ad,0xb552b61a,0x2d0026ad,
  0x2f8c309f,0xaddcac2e,0xb371b487,0x31cf3029,0x2c2e2ddc,0xb09faf8c,0xb029b1cf,0x34873371,0x22ad2902,0xb257b17a,0xa6adad00,0x361a3552,
  0x30d23194,0xa86ba1e4,0xb4b7b56a,0x2c6a25e4,0x2ea73012,0xad2aab5f,0xb294b402,0x31222f59,0x2b5f2d2a,0xb012aea7,0xaf59b122,0x34023294,
  0x21e4286b,0xb194b0d2,0xa5e4ac6a,0x356a34b7,0x302c30d2,0xa7a9a11b,0xb41ab4b7,0x2ba7251b,0x2dc22f0c,0xac79aa63,0xb1b6b2f7,0x30742e5f,
  0x2a632c79,0xaf0cadc2,0xae5fb074,0x32f731b6,0x211b27a9,0xb0d2b02c,0xa51baba7,0x34b7341a,0x2f0c3012,0xa67ba052,0xb2f7b402,0x2a7a2452,
  0x2cde2df5,0xab91a967,0xb0d7b1e8,0x2f8b2d65,0x29672b91,0xadf5acde,0xad65af8b,0x31e830d7,0x2052267b,0xb012af0c,0xa452aa7a,0x340232f7,
  0x2dc22ea7,0xa54d9f12,0xb1b6b294,0x294d2311,0x2bf62cde,0xaa31a86b,0xafefb0d7,0x2e2d2c6a,0x286b2a31,0xacdeabf6,0xac6aae2d,0x30d72fef,
  0x1f12254d,0xaea7adc2,0xa311a94d,0x329431b6,0x2c792d2a,0xa4209d7f,0xb074b122,0x281f217f,0x2a312b91,0xa8d0a6e0,0xae2daf8b,0x2cce2ade,
  0x26e028d0,0xab91aa31,0xaadeacce,0x2f8b2e2d,0x1d7f2420,0xad2aac79,0xa17fa81f,0x31223074,0x2a632b5f,0xa1e49bdb,0xae5faf59,0x25e41fdb,
  0x286b2967,0xa6e0a4e9,0xac6aad65,0x2ade28e8,0x24e926e0,0xa967a86b,0xa8e8aade,0x2d652c6a,0x1bdb21e4,0xab5faa63,0x9fdba5e4,0x2f592e5f,
  0x27a9286b,0x9f1298b6,0xaba7ac6a,0x23111cb6,0x254d267b,0xa420a1e4,0xa94daa7a,0x281f25e4,0x21e42420,0xa67ba54d,0xa5e4a81f,0x2a7a294d,
  0x18b61f12,0xa86ba7a9,0x9cb6a311,0x2c6a2ba7,0x211b21e4,0x98b69248,0xa51ba5e4,0x1cb61648,0x1f122052,0x9d7f9bdb,0xa311a452,0x217f1fdb,
  0x1bdb1d7f,0xa0529f12,0x9fdba17f,0x24522311,0x124818b6,0xa1e4a11b,0x96489cb6,0x25e4251b,0xa11ba1e4,0x18b61248,0x251b25e4,0x9cb69648,
  0x9f12a052,0x1d7f1bdb,0x23112452,0xa17f9fdb,0x9bdb9d7f,0x20521f12,0x1fdb217f,0xa452a311,0x924898b6,0x21e4211b,0x16481cb6,0xa5e4a51b,
  0xa7a9a86b,0x1f1218b6,0x2ba72c6a,0xa3119cb6,0xa54da67b,0x242021e4,0x294d2a7a,0xa81fa5e4,0xa1e4a420,0x267b254d,0x25e4281f,0xaa7aa94d,
  0x98b69f12,0x286b27a9,0x1cb62311,0xac6aaba7,0xaa63ab5f,0x21e41bdb,0x2e5f2f59,0xa5e49fdb,0xa86ba967,0x26e024e9,0x2c6a2d65,0xaadea8e8,
  0xa4e9a6e0,0x2967286b,0x28e82ade,0xad65ac6a,0x9bdba1e4,0x2b5f2a63,0x1fdb25e4,0xaf59ae5f,0xac79ad2a,0x24201d7f,0x30743122,0xa81fa17f,
  0xaa31ab91,0x28d026e0,0x2e2d2f8b,0xacceaade,0xa6e0a8d0,0x2b912a31,0x2ade2cce,0xaf8bae2d,0x9d7fa420,0x2d2a2c79,0x217f281f,0xb122b074,
  0xadc2aea7,0x254d1f12,0x31b63294,0xa94da311,0xabf6acde,0x2a31286b,0x2fef30d7,0xae2dac6a,0xa86baa31,0x2cde2bf6,0x2c6a2e2d,0xb0d7afef,
  0x9f12a54d,0x2ea72dc2,0x2311294d,0xb294b1b6,0xaf0cb012,0x267b2052,0x32f73402,0xaa7aa452,0xacdeadf5,0x2b912967,0x30d731e8,0xaf8bad65,
  0xa967ab91,0x2df52cde,0x2d652f8b,0xb1e8b0d7,0xa052a67b,0x30122f0c,0x24522a7a,0xb402b2f7,0xb02cb0d2,0x27a9211b,0x341a34b7,0xaba7a51b,
  0xadc2af0c,0x2c792a63,0x31b632f7,0xb074ae5f,0xaa63ac79,0x2f0c2dc2,0x2e5f3074,0xb2f7b1b6,0xa11ba7a9,0x30d2302c,0x251b2ba7,0xb4b7b41a,
  0xb0d2b194,0x286b21e4,0x34b7356a,0xac6aa5e4,0xaea7b012,0x2d2a2b5f,0x32943402,0xb122af59,0xab5fad2a,0x30122ea7,0x2f593122,0xb402b294,
  0xa1e4a86b,0x319430d2,0x25e42c6a,0xb56ab4b7,0xb17ab257,0x290222ad,0x3552361a,0xad00a6ad,0xaf8cb09f,0x2ddc2c2e,0x33713487,0xb1cfb029,
  0xac2eaddc,0x309f2f8c,0x302931cf,0xb487b371,0xa2ada902,0x3257317a,0x26ad2d00,0xb61ab552,0xb223b31c,0x29992376,0x35eb36c6,0xad97a776,
  0xb039b12d,0x2e8d2cac,0x3426350b,0xb27cb0a6,0xacacae8d,0x312d3039,0x30a6327c,0xb50bb426,0xa376a999,0x331c3223,0x27762d97,0xb6c6b5eb,
  0xb2cdb3e3,0x2a312420,0x3682376f,0xae2da81f,0xb0acb1bb,0x2f3f2d2a,0x3493358d,0xb328b122,0xad2aaf3f,0x31bb30ac,0x31223328,0xb58db493,
  0xa420aa31,0x33e332cd,0x281f2e2d,0xb76fb682,0xb378b456,0x2ac82484,0x3715380a,0xaec3a884,0xb120b24a,0x2ff22da9,0x34ff360e,0xb3d3b19e,
  0xada9aff2,0x324a3120,0x319e33d3,0xb60eb4ff,0xa484aac8,0x34563378,0x28842ec3,0xb80ab715,0xb413b4bc,0x2b5f24e9,0x37a6385a,0xaf59a8e8,
  0xb194b2da,0x30522e28,0x356a368d,0xb43eb219,0xae28b052,0x32da3194,0x3219343e,0xb68db56a,0xa4e9ab5f,0x34bc3413,0x28e82f59,0xb85ab7a6,
  0xb46ab523,0x2bf6254d,0x381a38a8,0xafefa94d,0xb209b36b,0x30ac2ea7,0x35d4370a,0xb493b294,0xaea7b0ac,0x336b3209,0x32943493,0xb70ab5d4,
  0xa54dabf6,0x3523346a,0x294d2fef,0xb8a8b81a,0xb4c3b58c,0x2c4725b2,0x385f38f3,0xb042a9b1,0xb27eb3fd,0x31062f26,0x363c3785,0xb4e7b30f,
  0xaf26b106,0x33fd327e,0x330f34e7,0xb785b63c,0xa5b2ac47,0x358c34c3,0x29b13042,0xb8f3b85f,0xb51cb5f6,0x2c932617,0x38a3393c,0xb08daa16,
  0xb2f4b448,0x31602fa5,0x36a437fe,0xb53ab389,0xafa5b160,0x344832f4,0x3389353a,0xb7feb6a4,0xa617ac93,0x35f6351c,0x2a16308d,0xb93cb8a3,
};
__device__ __align__(128) const uint32_t c_img[2560] = {
  0x326d31ed,0x333b32dd,0x33c33388,0x33fe33ea,0x33c331ed,0x31ed33c3,0xa8b22d64,0xb33bb0c4,0x33ea31ed,0xad64301d,0xb2ddb388,0x315fa8b2,
  0x32dd31ed,0xb3feabc6,0x326dad64,0xad64326d,0x30c431ed,0xaed7b2dd,0x2bc63388,0xa248b3ea,0x2bc631ed,0x315fb3c3,0xb3ea2d64,0x2ed730c4,
  0xa8b231ed,0x3388b01d,0x301db388,0xb1ed28b2,0xb01d31ed,0x22482bc6,0x30c4ad64,0x3388b26d,0x33ea33fe,0x338833c3,0x32dd333b,0x31ed326d,
  0xb2ddb3fe,0xa248b01d,0x326d2ed7,0x338833ea,0x30c433fe,0xb33babc6,0xabc6b33b,0x33fe30c4,0xabc6b3fe,0x31ed32dd,0xb3eaaed7,0x333ba8b2,
  0xa8b233fe,0x2d64b3c3,0xb01d333b,0x315fb26d,0x301db3fe,0xb3fe301d,0x30c42ed7,0x2d64b3ea,0xb26d33fe,0x2ed72bc6,0x33c3b33b,0xa248b0c4,
  0x33c3b3fe,0x315fb2dd,0x28b2aed7,0xaed728b2,0xb0c4b15f,0xaed7b01d,0xabc6ad64,0xa248a8b2,0xabc6b15f,0x315f2bc6,0x33ea3388,0x2ed7326d,
  0x28b2b15f,0x338832dd,0xb01d2d64,0xb1edb3ea,0x301db15f,0x224833c3,0xb0c4b388,0x338830c4,0x326db15f,0xb33b301d,0x33c3ad64,0xb3fe28b2,
  0x33c3b15f,0xb1edabc6,0xa8b23388,0x333bb26d,0x33eab15f,0x2d64b2dd,0xb2dd2d64,0xb15f33ea,0x32ddb15f,0x33feb3c3,0x326db388,0x2d64b0c4,
  0x28b22248,0x2d642bc6,0x301d2ed7,0x315f30c4,0xb01da248,0xb3feb2dd,0xb0c4b33b,0x2d64a8b2,0x326d2248,0x2ed733c3,0xb3c3aed7,0xa248b26d,
  0xb3c3a248,0x315fb01d,0xa8b2333b,0xaed7b3ea,0x33ea2248,0xb388abc6,0x32dd2ed7,0xb1edb0c4,0xb2dda248,0x224832dd,0x326db33b,0xb38828b2,
  0x30c42248,0x333bb3c3,0xabc6aed7,0xb3fe326d,0xabc6a248,0xb1ed301d,0xb3ea333b,0xb33b33ea,0xb26d31ed,0xb33b32dd,0xb3c33388,0xb3fe33ea,
  0xb3c331ed,0xb1ed33c3,0x28b22d64,0x333bb0c4,0xb3ea31ed,0x2d64301d,0x32ddb388,0xb15fa8b2,0xb2dd31ed,0x33feabc6,0xb26dad64,0x2d64326d,
  0xb0c431ed,0x2ed7b2dd,0xabc63388,0x2248b3ea,0xabc631ed,0xb15fb3c3,0x33ea2d64,0xaed730c4,0x28b231ed,0xb388b01d,0xb01db388,0x31ed28b2,
  0x301d31ed,0xa2482bc6,0xb0c4ad64,0xb388b26d,0xb3ea33fe,0xb38833c3,0xb2dd333b,0xb1ed326d,0x32ddb3fe,0x2248b01d,0xb26d2ed7,0xb38833ea,
  0xb0c433fe,0x333babc6,0x2bc6b33b,0xb3fe30c4,0x2bc6b3fe,0xb1ed32dd,0x33eaaed7,0xb33ba8b2,0x28b233fe,0xad64b3c3,0x301d333b,0xb15fb26d,
  0xb01db3fe,0x33fe301d,0xb0c42ed7,0xad64b3ea,0x326d33fe,0xaed72bc6,0xb3c3b33b,0x2248b0c4,0xb3c3b3fe,0xb15fb2dd,0xa8b2aed7,0x2ed728b2,
  0x30c4b15f,0x2ed7b01d,0x2bc6ad64,0x2248a8b2,0x2bc6b15f,0xb15f2bc6,0xb3ea3388,0xaed7326d,0xa8b2b15f,0xb38832dd,0x301d2d64,0x31edb3ea,
  0xb01db15f,0xa24833c3,0x30c4b388,0xb38830c4,0xb26db15f,0x333b301d,0xb3c3ad64,0x33fe28b2,0xb3c3b15f,0x31edabc6,0x28b23388,0xb33bb26d,
  0xb3eab15f,0xad64b2dd,0x32dd2d64,0x315f33ea,0xb2ddb15f,0xb3feb3c3,0xb26db388,0xad64b0c4,0xa8b22248,0xad642bc6,0xb01d2ed7,0xb15f30c4,
  0x301da248,0x33feb2dd,0x30c4b33b,0xad64a8b2,0xb26d2248,0xaed733c3,0x33c3aed7,0x2248b26d,0x33c3a248,0xb15fb01d,0x28b2333b,0x2ed7b3ea,
  0xb3ea2248,0x3388abc6,0xb2dd2ed7,0x31edb0c4,0x32dda248,0xa24832dd,0xb26db33b,0x338828b2,0xb0c42248,0xb33bb3c3,0x2bc6aed7,0x33fe326d,
  0x2bc6a248,0x31ed301d,0x33ea333b,0x333b33ea,0x30c4315f,0x2ed7301d,0x2bc62d64,0x224828b2,0x2bc6315f,0xb15fabc6,0xb3eab388,0xaed7b26d,
  0xa8b2315f,0xb388b2dd,0x301dad64,0x31ed33ea,0xb01d315f,0xa248b3c3,0x30c43388,0xb388b0c4,0xb26d315f,0x333bb01d,0xb3c32d64,0x33fea8b2,
  0xb3c3315f,0x31ed2bc6,0x28b2b388,0xb33b326d,0xb3ea315f,0xad6432dd,0x32ddad64,0x315fb3ea,0xb2dd315f,0xb3fe33c3,0xb26d3388,0xad6430c4,
  0xa8b2a248,0xad64abc6,0xb01daed7,0xb15fb0c4,0x301d2248,0x33fe32dd,0x30c4333b,0xad6428b2,0xb26da248,0xaed7b3c3,0x33c32ed7,0x2248326d,
  0x33c32248,0xb15f301d,0x28b2b33b,0x2ed733ea,0xb3eaa248,0x33882bc6,0xb2ddaed7,0x31ed30c4,0x32dd2248,0xa248b2dd,0xb26d333b,0x3388a8b2,
  0xb0c4a248,0xb33b33c3,0x2bc62ed7,0x33feb26d,0x2bc62248,0x31edb01d,0x33eab33b,0x333bb3ea,0x326d31ed,0x333b32dd,0x33c33388,0x33fe33ea,
  0x33c331ed,0x31ed33c3,0xa8b22d64,0xb33bb0c4,0x33ea31ed,0xad64301d,0xb2ddb388,0x315fa8b2,0x32dd31ed,0xb3feabc6,0x326dad64,0xad64326d,
  0x30c431ed,0xaed7b2dd,0x2bc63388,0xa248b3ea,0x2bc631ed,0x315fb3c3,0xb3ea2d64,0x2ed730c4,0xa8b231ed,0x3388b01d,0x301db388,0xb1ed28b2,
  0xb01d31ed,0x22482bc6,0x30c4ad64,0x3388b26d,0x33ea33fe,0x338833c3,0x32dd333b,0x31ed326d,0xb2ddb3fe,0xa248b01d,0x326d2ed7,0x338833ea,
  0x30c433fe,0xb33babc6,0xabc6b33b,0x33fe30c4,0xabc6b3fe,0x31ed32dd,0xb3eaaed7,0x333ba8b2,0xa8b233fe,0x2d64b3c3,0xb01d333b,0x315fb26d,
  0x301db3fe,0xb3fe301d,0x30c42ed7,0x2d64b3ea,0xb26d33fe,0x2ed72bc6,0x33c3b33b,0xa248b0c4,0x33c3b3fe,0x315fb2dd,0x28b2aed7,0xaed728b2,
  0xb0c4315f,0xaed7301d,0xabc62d64,0xa24828b2,0xabc6315f,0x315fabc6,0x33eab388,0x2ed7b26d,0x28b2315f,0x3388b2dd,0xb01dad64,0xb1ed33ea,
  0x301d315f,0x2248b3c3,0xb0c43388,0x3388b0c4,0x326d315f,0xb33bb01d,0x33c32d64,0xb3fea8b2,0x33c3315f,0xb1ed2bc6,0xa8b2b388,0x333b326d,
  0x33ea315f,0x2d6432dd,0xb2ddad64,0xb15fb3ea,0x32dd315f,0x33fe33c3,0x326d3388,0x2d6430c4,0x28b2a248,0x2d64abc6,0x301daed7,0x315fb0c4,
  0xb01d2248,0xb3fe32dd,0xb0c4333b,0x2d6428b2,0x326da248,0x2ed7b3c3,0xb3c32ed7,0xa248326d,0xb3c32248,0x315f301d,0xa8b2b33b,0xaed733ea,
  0x33eaa248,0xb3882bc6,0x32ddaed7,0xb1ed30c4,0xb2dd2248,0x2248b2dd,0x326d333b,0xb388a8b2,0x30c4a248,0x333b33c3,0xabc62ed7,0xb3feb26d,
  0xabc62248,0xb1edb01d,0xb3eab33b,0xb33bb3ea,0xb26d31ed,0xb33b32dd,0xb3c33388,0xb3fe33ea,0xb3c331ed,0xb1ed33c3,0x28b22d64,0x333bb0c4,
  0xb3ea31ed,0x2d64301d,0x32ddb388,0xb15fa8b2,0xb2dd31ed,0x33feabc6,0xb26dad64,0x2d64326d,0xb0c431ed,0x2ed7b2dd,0xabc63388,0x2248b3ea,
  0xabc631ed,0xb15fb3c3,0x33ea2d64,0xaed730c4,0x28b231ed,0xb388b01d,0xb01db388,0x31ed28b2,0x301d31ed,0xa2482bc6,0xb0c4ad64,0xb388b26d,
  0xb3ea33fe,0xb38833c3,0xb2dd333b,0xb1ed326d,0x32ddb3fe,0x2248b01d,0xb26d2ed7,0xb38833ea,0xb0c433fe,0x333babc6,0x2bc6b33b,0xb3fe30c4,
  0x2bc6b3fe,0xb1ed32dd,0x33eaaed7,0xb33ba8b2,0x28b233fe,0xad64b3c3,0x301d333b,0xb15fb26d,0xb01db3fe,0x33fe301d,0xb0c42ed7,0xad64b3ea,
  0x326d33fe,0xaed72bc6,0xb3c3b33b,0x2248b0c4,0xb3c3b3fe,0xb15fb2dd,0xa8b2aed7,0x2ed728b2,0x29ed29ed,0x29ed29ed,0x29ed29ed,0x29ed29ed,
  0x2bc32a6d,0x2add2bea,0x23c628c4,0xa81da0b2,0x2bc32add,0xa3c6281d,0xabc3aadd,0x23c6a81d,0x29ed2b3b,0xabfea564,0x295fa6d7,0x1a482b88,
  0x25642b88,0xa564ab88,0x25642b88,0xa564ab88,0xa0b22bc3,0x2a6daadd,0xabea23c6,0x28c4281d,0xa8c42bea,0x2a6da0b2,0x28c4abea,0xaa6d20b2,
  0xab3b2bfe,0xa564295f,0x26d79a48,0x2b88a9ed,0x29ed29ed,0x29ed29ed,0x29ed29ed,0x29ed29ed,0xabc3aa6d,0xaaddabea,0xa3c6a8c4,0x281d20b2,
  0x2bc32add,0xa3c6281d,0xabc3aadd,0x23c6a81d,0xa9edab3b,0x2bfe2564,0xa95f26d7,0x9a48ab88,0x25642b88,0xa564ab88,0x25642b88,0xa564ab88,
  0x20b2abc3,0xaa6d2add,0x2beaa3c6,0xa8c4a81d,0xa8c42bea,0x2a6da0b2,0x28c4abea,0xaa6d20b2,0x2b3babfe,0x2564a95f,0xa6d71a48,0xab8829ed,
  0x295f295f,0x295f295f,0x295f295f,0x295f295f,0x23c628c4,0xa81da0b2,0xabc3aa6d,0xaaddabea,0xa3c6281d,0xabc3aadd,0x23c6a81d,0x2bc32add,
  0xa95f26d7,0x9a48ab88,0x29ed2b3b,0xabfea564,0xab882564,0x2b88a564,0xab882564,0x2b88a564,0xabea23c6,0x28c4281d,0x20b2abc3,0xaa6d2add,
  0xaa6d20b2,0xa8c42bea,0x2a6da0b2,0x28c4abea,0xa6d71a48,0xab8829ed,0xab3b2bfe,0xa564295f,0x295f295f,0x295f295f,0x295f295f,0x295f295f,
  0xa3c6a8c4,0x281d20b2,0x2bc32a6d,0x2add2bea,0xa3c6281d,0xabc3aadd,0x23c6a81d,0x2bc32add,0x295fa6d7,0x1a482b88,0xa9edab3b,0x2bfe2564,
  0xab882564,0x2b88a564,0xab882564,0x2b88a564,0x2beaa3c6,0xa8c4a81d,0xa0b22bc3,0x2a6daadd,0xaa6d20b2,0xa8c42bea,0x2a6da0b2,0x28c4abea,
  0x26d79a48,0x2b88a9ed,0x2b3babfe,0x2564a95f,0xabfe2bfe,0xabfe2bfe,0xabfe2bfe,0xabfe2bfe,0xaadd2bea,0xa3c628c4,0x281da0b2,0x2bc3aa6d,
  0xa81d2bc3,0x2adda3c6,0x281dabc3,0xaadd23c6,0x9a482b88,0x29edab3b,0xabfe2564,0x295f26d7,0x26d72b3b,0xa6d7ab3b,0x26d72b3b,0xa6d7ab3b,
  0x2a6d2add,0xabeaa3c6,0x28c4a81d,0x20b22bc3,0x2bea2a6d,0xa0b228c4,0xabeaaa6d,0x20b2a8c4,0x2b8829ed,0x2b3b2bfe,0x2564295f,0xa6d79a48,
  0xabfe2bfe,0xabfe2bfe,0xabfe2bfe,0xabfe2bfe,0x2addabea,0x23c6a8c4,0xa81d20b2,0xabc32a6d,0xa81d2bc3,0x2adda3c6,0x281dabc3,0xaadd23c6,
  0x1a48ab88,0xa9ed2b3b,0x2bfea564,0xa95fa6d7,0x26d72b3b,0xa6d7ab3b,0x26d72b3b,0xa6d7ab3b,0xaa6daadd,0x2bea23c6,0xa8c4281d,0xa0b2abc3,
  0x2bea2a6d,0xa0b228c4,0xabeaaa6d,0x20b2a8c4,0xab88a9ed,0xab3babfe,0xa564a95f,0x26d71a48,0x1a489a48,0x1a489a48,0x1a489a48,0x1a489a48,
  0x281da0b2,0x2bc3aa6d,0x2addabea,0x23c6a8c4,0x2adda3c6,0x281dabc3,0xaadd23c6,0xa81d2bc3,0x2bfea564,0xa95fa6d7,0x9a482b88,0x29edab3b,
  0x2b3ba6d7,0xab3b26d7,0x2b3ba6d7,0xab3b26d7,0x28c4a81d,0x20b22bc3,0xaa6daadd,0x2bea23c6,0x20b2a8c4,0x2bea2a6d,0xa0b228c4,0xabeaaa6d,
  0xa564a95f,0x26d71a48,0x2b8829ed,0x2b3b2bfe,0x1a489a48,0x1a489a48,0x1a489a48,0x1a489a48,0xa81d20b2,0xabc32a6d,0xaadd2bea,0xa3c628c4,
  0x2adda3c6,0x281dabc3,0xaadd23c6,0xa81d2bc3,0xabfe2564,0x295f26d7,0x1a48ab88,0xa9ed2b3b,0x2b3ba6d7,0xab3b26d7,0x2b3ba6d7,0xab3b26d7,
  0xa8c4281d,0xa0b2abc3,0x2a6d2add,0xabeaa3c6,0x20b2a8c4,0x2bea2a6d,0xa0b228c4,0xabeaaa6d,0x2564295f,0xa6d79a48,0xab88a9ed,0xab3babfe,
  0xa95fa95f,0xa95fa95f,0xa95fa95f,0xa95fa95f,0xa3c6a8c4,0x281d20b2,0x2bc32a6d,0x2add2bea,0x23c6a81d,0x2bc32add,0xa3c6281d,0xabc3aadd,
  0x295fa6d7,0x1a482b88,0xa9edab3b,0x2bfe2564,0x2b88a564,0xab882564,0x2b88a564,0xab882564,0x2beaa3c6,0xa8c4a81d,0xa0b22bc3,0x2a6daadd,
  0x2a6da0b2,0x28c4abea,0xaa6d20b2,0xa8c42bea,0x26d79a48,0x2b88a9ed,0x2b3babfe,0x2564a95f,0xa95fa95f,0xa95fa95f,0xa95fa95f,0xa95fa95f,
  0x23c628c4,0xa81da0b2,0xabc3aa6d,0xaaddabea,0x23c6a81d,0x2bc32add,0xa3c6281d,0xabc3aadd,0xa95f26d7,0x9a48ab88,0x29ed2b3b,0xabfea564,
  0x2b88a564,0xab882564,0x2b88a564,0xab882564,0xabea23c6,0x28c4281d,0x20b2abc3,0xaa6d2add,0x2a6da0b2,0x28c4abea,0xaa6d20b2,0xa8c42bea,
  0xa6d71a48,0xab8829ed,0xab3b2bfe,0xa564295f,0x29ed29ed,0x29ed29ed,0x29ed29ed,0x29ed29ed,0x2bc32a6d,0x2add2bea,0x23c628c4,0xa81da0b2,
  0x2bc32add,0xa3c6281d,0xabc3aadd,0x23c6a81d,0x29ed2b3b,0xabfea564,0x295fa6d7,0x1a482b88,0x25642b88,0xa564ab88,0x25642b88,0xa564ab88,
  0xa0b22bc3,0x2a6daadd,0xabea23c6,0x28c4281d,0xa8c42bea,0x2a6da0b2,0x28c4abea,0xaa6d20b2,0xab3b2bfe,0xa564295f,0x26d79a48,0x2b88a9ed,
  0x29ed29ed,0x29ed29ed,0x29ed29ed,0x29ed29ed,0xabc3aa6d,0xaaddabea,0xa3c6a8c4,0x281d20b2,0x2bc32add,0xa3c6281d,0xabc3aadd,0x23c6a81d,
  0xa9edab3b,0x2bfe2564,0xa95f26d7,0x9a48ab88,0x25642b88,0xa564ab88,0x25642b88,0xa564ab88,0x20b2abc3,0xaa6d2add,0x2beaa3c6,0xa8c4a81d,
  0xa8c42bea,0x2a6da0b2,0x28c4abea,0xaa6d20b2,0x2b3babfe,0x2564a95f,0xa6d71a48,0xab8829ed,0x9a481a48,0x9a481a48,0x9a481a48,0x9a481a48,
  0xa81d20b2,0xabc32a6d,0xaadd2bea,0xa3c628c4,0xaadd23c6,0xa81d2bc3,0x2adda3c6,0x281dabc3,0xabfe2564,0x295f26d7,0x1a48ab88,0xa9ed2b3b,
  0xab3b26d7,0x2b3ba6d7,0xab3b26d7,0x2b3ba6d7,0xa8c4281d,0xa0b2abc3,0x2a6d2add,0xabeaa3c6,0xa0b228c4,0xabeaaa6d,0x20b2a8c4,0x2bea2a6d,
  0x2564295f,0xa6d79a48,0xab88a9ed,0xab3babfe,0x9a481a48,0x9a481a48,0x9a481a48,0x9a481a48,0x281da0b2,0x2bc3aa6d,0x2addabea,0x23c6a8c4,
  0xaadd23c6,0xa81d2bc3,0x2adda3c6,0x281dabc3,0x2bfea564,0xa95fa6d7,0x9a482b88,0x29edab3b,0xab3b26d7,0x2b3ba6d7,0xab3b26d7,0x2b3ba6d7,
  0x28c4a81d,0x20b22bc3,0xaa6daadd,0x2bea23c6,0xa0b228c4,0xabeaaa6d,0x20b2a8c4,0x2bea2a6d,0xa564a95f,0x26d71a48,0x2b8829ed,0x2b3b2bfe,
  0xabfe2bfe,0xabfe2bfe,0xabfe2bfe,0xabfe2bfe,0xaadd2bea,0xa3c628c4,0x281da0b2,0x2bc3aa6d,0xa81d2bc3,0x2adda3c6,0x281dabc3,0xaadd23c6,
  0x9a482b88,0x29edab3b,0xabfe2564,0x295f26d7,0x26d72b3b,0xa6d7ab3b,0x26d72b3b,0xa6d7ab3b,0x2a6d2add,0xabeaa3c6,0x28c4a81d,0x20b22bc3,
  0x2bea2a6d,0xa0b228c4,0xabeaaa6d,0x20b2a8c4,0x2b8829ed,0x2b3b2bfe,0x2564295f,0xa6d79a48,0xabfe2bfe,0xabfe2bfe,0xabfe2bfe,0xabfe2bfe,
  0x2addabea,0x23c6a8c4,0xa81d20b2,0xabc32a6d,0xa81d2bc3,0x2adda3c6,0x281dabc3,0xaadd23c6,0x1a48ab88,0xa9ed2b3b,0x2bfea564,0xa95fa6d7,
  0x26d72b3b,0xa6d7ab3b,0x26d72b3b,0xa6d7ab3b,0xaa6daadd,0x2bea23c6,0xa8c4281d,0xa0b2abc3,0x2bea2a6d,0xa0b228c4,0xabeaaa6d,0x20b2a8c4,
  0xab88a9ed,0xab3babfe,0xa564a95f,0x26d71a48,0x3bfb3bff,0x3be53bf2,0x3bbf3bd4,0x3b873ba5,0x3bd03bfb,0x3b013b7c,0x399d3a60,0x378538bc,
  0x35173b52,0xbbc9b7c8,0xb074ba9b,0x3bfe391b,0x319e3b27,0xbbf3b979,0x363cb80a,0x3a2d3bc5,0xba093986,0x3a7eb8f8,0xbae5385f,0x3b3db77a,
  0xbabd393c,0x3bb0b699,0xbc00305b,0x3ba730d7,0xbb2a35c8,0xb8353bb2,0x3a64b1e8,0x3962bbf7,0xba90350b,0xba413bff,0x3602340e,0x3bf6bad8,
  0xac6aa5e4,0xb122af59,0xb402b294,0xb56ab4b7,0xb2deac9c,0xb7bdb5a5,0xb9b3b8d6,0xbb10ba73,0xbb96b676,0xb359bafe,0x3bec3884,0x2a163a29,
  0xbbe0b72c,0x2f27b9d6,0x3b5e3ae8,0xb91633a2,0xb941b9c9,0x38ad3a45,0xb80fbab3,0x36d23b13,0xb850ba0d,0x346f3b4a,0x1fdbbbed,0xb4ab3be8,
  0x3721bb76,0xbace3463,0xb8d13bdd,0x39ebadfb,0x3894bb98,0xb8fd281f,0xbb6a3bbd,0x2e2d3825,0x3b3f3b65,0x3ae83b16,0x3a813ab6,0x3a0d3a49,
  0x3263356a,0xad972b43,0xb5dfb359,0xb8eeb7f3,0xa9b139aa,0xbbedba25,0x3340b889,0x3b983afb,0xbaa2aa16,0xb4cfbb8e,0x3c0038ad,0xb44b38e5,
  0xbb853625,0x3bbdb4c3,0xbbe432ad,0x3bfbaf8b,0xbaacb6d2,0x39243954,0xb65fbace,0x2fbd3bb8,0xb9661648,0xba603bf8,0x383a31cf,0x3b27bbb3,
  0x3219b9eb,0xbb1836f4,0xb9903be5,0x37dd3010,0xb6c6b61a,0xb80ab76f,0xb8a8b85a,0xb93cb8f3,0xbbd7bb87,0xbbf8bbfd,0xbb71bbc9,0xba4dbaf1,
  0xbbfeb9a6,0x305bb91f,0x3bcb3a97,0xb50b37d2,0xb87abbfe,0x3ba13546,0x24523a7e,0xbbb5ba54,0xb576bb63,0x340e3ba3,0xb13bbbd3,0x2c9c3bf2,
  0x386abb3d,0xba2139f8,0x3b57b835,0xbbf13432,0x39e7bc00,0xb8d6adc9,0xbacb3bde,0x372c3457,0x3bdab962,0x3764bb35,0xb9c03122,0xbaf73bef,
  0x398b39cd,0x38fd3946,0x386538b2,0x37853815,0xba85b9c9,0xbb92bb1e,0xbbfebbdd,0xbbc2bbf5,0xb66b3682,0xbb01bb94,0x387fb371,0x3a2d3beb,
  0xbac7bb76,0x3a00ad33,0x36bb3bd4,0xbbeab79b,0xbc0026ad,0x3bf32c38,0xbbd6b109,0x3ba733eb,0x3153bbff,0xb70a3b9e,0x396bba9b,0xbade390c,
  0xb5d4b5bc,0xbbb03b2c,0x32013830,0x3bf6ba67,0x3bccbb52,0x2c06b92e,0xbb83385f,0xb8c73bab,0xb9c5b982,0xba41ba04,0xbab0ba7a,0xbb10bae1,
  0xb8a3b986,0xb52fb74e,0xa94db1e8,0x33d32e91,0xbb54bb4f,0x37bdb523,0x3a9e3bc8,0xb916308d,0x3840b5c8,0x394a3bf9,0xbb42b294,0xb0a6bb0a,
  0x251bbbff,0xaf273bfc,0x327cbbe6,0xb4ab3bc0,0x3be325e4,0xbb2fb4e7,0x39e33884,0xb81aba35,0x3b73bb78,0xb46fb715,0xbbdc3ad1,0x2e2d38cc,
  0x33283676,0x3bfcba19,0x3581bab3,0xba6b3493,0x363136dd,0x34cf3581,0x32c6341a,0x2fbd3153,0xbae1bb65,0xb970ba39,0xb715b889,0xb16cb4f3,
  0xb9a12a7a,0xb924bbfe,0x3a933042,0x37dd3bcc,0x308db9aa,0x3b453b07,0xb94632ad,0xb845bbfa,0xbb68b55e,0x3b1836bb,0xbabab805,0x3a4d38a3,
  0x3bc0b625,0xbbfe2ec3,0x3b9431cf,0xba89b742,0x9cb6b95d,0xbbf8396b,0xb1b63a5c,0x3bb5b840,0x38cc9648,0x3b81bbac,0xac38b85a,0xbbce3933,
  0xbb60bb3a,0xbba1bb83,0xbbd2bbbc,0xbbf1bbe3,0x3815361a,0x39df3907,0x3b2c3a97,0x3be23b9c,0xb9afbbfd,0x3a21294d,0x388e3bee,0xbaf7b328,
  0x3beb39a6,0xb6af37a6,0xba04bbd3,0x3ac42d00,0x360ebb89,0xb7643b42,0x3855baeb,0xb8ee3a85,0x33eb3b63,0x28e8bbf5,0xb5233bde,0x389ebb21,
  0x3c00b9f0,0x2d97b9e3,0xbbdf38db,0xb44b3ac7,0xba673c00,0x358d3487,0x3bfcbab6,0x330fba15,0x3b7a3bf1,0x394a3a93,0x33893764,0xb3d39cb6,
  0x3afb3be2,0x35eb3946,0xb4c328e8,0xbaa9b8cc,0x27763af7,0xbb2fbaba,0x3a76ad97,0x30a63b60,0xaf8b3ac4,0xb994bb94,0x3bf8358d,0xb8743815,
  0xbb4c38ee,0x3bfcb1b6,0xbad5b4cf,0x381a39af,0xbbb3389e,0x3b592c38,0xb76fb970,0xb24b3beb,0xb9d2344b,0xbb923bd2,0xb0f03924,0x3a6bb60e,
  0xb8f3330f,0xbc003b2c,0xb91f3b45,0x323233eb,0xb5b1afbd,0xba00b88e,0xbbc6bb18,0xbbc2bc00,0xb7d2b16c,0xbb6fba04,0xbba3bbfe,0xb86fba67,
  0xbbffb7dd,0x370ab855,0x38b73bf8,0xbbeab631,0xbbf2b845,0x39bcb523,0x2dc93b81,0xbaa5bae1,0xb68dba4d,0xac063bdf,0x382abba1,0xbade39a1,
  0xb457ba89,0xb6543bfc,0x3b16b9df,0xbbd8308d,0x397dbbb5,0xb52fb2c6,0xbbe73a21,0xb8c73b68,0x3a49bbce,0x2311b715,0xba2536af,0xbbd93bc0,
  0xb958b785,0xbb81ba9e,0xbbefbbf3,0xba89bb73,0xbbf7bbc2,0xb9b8bb42,0xaf59b70a,0x384a3328,0xbb8bba2d,0x39dfb27c,0x34263bb0,0xbbceb98b,
  0xb4b7bbea,0x3b6c39e3,0xbafe2c06,0x3185ba85,0xaadebba7,0xb6af3bdc,0x3a58ba41,0xbbe2366b,0x3a29bade,0xbc003581,0x3a45352f,0xb2f7bac7,
  0x3b37bbf6,0x28e8b865,0xbaee37bd,0xbac43c00,0x3b13b8c7,0x3b5cbbfe,0x3463b94a,0xb8993153,0xb9f4bb10,0xb58db87f,0x3029af27,0x389e35d4,
  0x2dfbb3d3,0x399936bb,0x3bf23b2f,0x3ac13bcc,0x3552b916,0x39703bd6,0xbbbab46f,0x330fb9c5,0x3ba530a6,0xb5f7396b,0xb7c8bbfc,0x3be138a3,
  0x3bfdb4ab,0xbb45b201,0x38e038fd,0xb16cbb54,0x391b381a,0xa17fbb83,0xb8f83b92,0x3bcfb840,0x36e82e2d,0x3bfebab0,0x37febb01,0xb845251b,
  0xb77a3a6b,0x3648294d,0x3bb2ba00,0x3a8cbbe3,0xb742b93c,0x2311b340,0x37a6340e,0x3aa93966,0x3b963a4d,0x3b7f3c00,0x380f3a21,0xb0be3219,
  0x3933b50b,0x35eb3be4,0xbbf5b8d6,0x3874b6c6,0x39413bb5,0xbbffb65f,0x38d1b764,0x33ba3bd7,0x3b9c2c9c,0xb994b83a,0x34873ae8,0x324bbbfe,
  0xb7213bf1,0x3b47b990,0xbbbf2d97,0x38c1387a,0x2d00372c,0x3b59b8a8,0x3a39bbed,0xb232b576,0xbbfb3af7,0xb9743b71,0x307434cf,0x3adbb86a,
  0x3b213a0d,0x3c003bcb,0x3b073bbd,0x386f39e7,0x351738ee,0xb599a452,0xbae5b924,0xbbe9bbda,0x3a153b98,0xbb6fb13b,0x2ec3ba60,0x3aa53b3f,
  0xba09344b,0xa884bb57,0x3a643b18,0xbbc3b263,0xb4f33bfb,0x39bcbacb,0xbbac380a,0x3bd8a9b1,0xbb2aafbd,0x36a439c0,0x3402bbf8,0xba6f3aa2,
  0xbbfa3b27,0xb6543a81,0x3907b05b,0x3bd9bb85,0x2c6ab7dd,0xb9da35df,0xbbec3ba1,0xb8203aac,0x3bf53b87,0x3b6c3bec,0x392e3a7e,0x32f73721,
  0xb9e7b785,0xbbfcbb5e,0xba81bbb0,0xb43eb894,0x379b3bfe,0xbc00b80f,0x374eb835,0x38993bfb,0xbb3fba2d,0x3b329fdb,0xb3403a41,0xb8eabbd0,
  0xb90c3b3d,0x3b5cb8d1,0xbbf93122,0x3ac13517,0x29b1bba7,0xb94f3b6a,0x3be4b7bd,0xbaf4b19e,0xbbab3962,0xb9993bbf,0x34e73359,0x3be1ba09,
  0x3b85bbf6,0x353ab99d,0xb83a2f27,0xbbf03abd,0x2e91356a,0xb5f7b074,0xba19b8ad,0xbbcfbb2a,0xb966bb10,0xaba7b63c,0x38a8346f,0x3bb73a90,
  0xbb0aaa16,0xa17fbae5,0x3b1e3ace,0xba8c2c6a,0x36c6b916,0x36ff3c00,0xbbcbb8fd,0x3a50b2de,0xba35b6d2,0x36483a64,0x2d33bbe5,0xb84a3b96,
  0x3bfeb4ab,0xb9fcb602,0x313b3b01,0x37e8bbe0,0x3493b9eb,0xb9b83402,0xbb9e3bc9,0xb1853941,0x35762e2d,0x3b90b9b3,0x3acbbbf3,0x2fefb850,
  0x3a543bcf,0x2884374e,0xb9f8b648,0xbbe9bbab,0x398b3bb7,0xb4db3340,0xbbdcb9fc,0xb911bb85,0xb4323a8c,0xb6a4bbf9,0x3b3539b8,0xbbc3ae91,
  0xb66b3a50,0xad65bbe4,0x38653b90,0xbb0db966,0xbbef384a,0x39da34e7,0x2b43bb6c,0xba6f3b0a,0xbc0037e8,0x3759383a,0x387fbbfc,0xbbf636c6,
  0xb7f33185,0xbb7f3a19,0xbb8e3c00,0xb8203a35,0xb5d42fef,0xba1d38a8,0xbbd63b32,0xbba93bfe,0xb8e5b2f7,0xbbffbb1e,0xb954bb5c,0x30beb493,
  0xb9c5b43e,0xbb9fbbcb,0xb201b94f,0x3a313576,0xbbb8b899,0x3b47ad33,0xb6f43999,0xb3babbf5,0xbb54b8ea,0x3bf9313b,0xbab0353a,0x3790b9e7,
  0xb010bac1,0xb9743b9e,0x3bfdb5f7,0xb8c1b79b,0x251bbaf4,0xbb1b3acb,0x3a9e2ba7,0x2e5fbb3f,0x3af1bbe1,0x3599b92e,0xb546a17f,0xbadb390c,
  0x3b73bbf0,0x3929ba81,0x327cb6ff,0xb49f29b1,0xb825baa9,0x353aaec3,0x3b7c3994,0x3af43bfa,0x360eb0be,0x3bf43a64,0x388e3b47,0xb7372c6a,
  0x38bcb874,0x2ba73bac,0xb979bb59,0x3bf03742,0x3c0033ba,0xbb043402,0x3855b974,0xacce3b96,0x3bc5b24b,0xb6ffb907,0xb6993c00,0x3bb7b933,
  0x363138c1,0x3902bbec,0xbbdf3599,0x34ff3941,0x30d73232,0x39fcb7a6,0x3bffbb6f,0x3a50bb9c,0xb9a13adb,0xb47b380f,0x32c62884,0x3937b721,
  0x3ad8386f,0x3b903bf5,0x35a539bc,0xb7e8ad00,0x3b683be9,0x2ef538d1,0xba93b6a4,0xbb24bbfb,0x3a733aa5,0xbbfcb487,0x39d6b654,0xafef3b21,
  0x1cb63bc3,0xb7b2bbbf,0x3aba39da,0xbbfab517,0xb3a23bd8,0x3b32ba39,0xbb4a2311,0x343e3a15,0xbb603a6f,0x3a3d3074,0x31b6bb7f,0xbb9a3a09,
  0xbbe83bd9,0xb94f3b07,0xa81f35eb,0x38eab4f3,0xb9af3820,0xbbae3ae5,0xbbd23bff,0xba113b2a,0x319e389e,0xb929b426,0xbc00bb45,0xb911bb37,
  0xbbffbac1,0xb805bafe,0x382a217f,0x3bfd3b13,0xbabd330f,0x34dbba58,0x36023bfe,0xbb0db9f4,0xb68dbbe1,0x3a5c3a45,0xbbe7b648,0x3b89adfb,
  0xba90b16c,0x2d653aee,0x39b3bb81,0xbbf63552,0x397dbbcf,0xbbbc3463,0x338939b8,0x39f0bba5,0x32deb845,0xb7593029,0xbb5e39df,0xbba93bfd,
  0x3b7aba8c,0x3beebbf2,0x3a76bb6c,0x36ddb91b,0xbbe0ba89,0xba1dbbba,0x1fdbb6af,0x3a3136e8,0xa776b84a,0x3aeb37c8,0x3ad53c00,0xaa7a377a,
  0xb850bbce,0x3b9f38e0,0xbb6a28e8,0x3790b958,0x3b4cb185,0xb8db38f8,0x30f0bb5c,0x355e3bf7,0x3894bbe2,0xbbf937fe,0x399d358d,0x2e5fbb8b,
  0x39d232f7,0x341abbb2,0xbbc63999,0x395d34b7,0x3bd0bac4,0x3b1bbbef,0x363cb970,0xb49faade,0xb5b13899,0x30422f59,0x38b7b5f7,0x3b3aba29,
  0x3219b3d3,0x3b0438b7,0x3b713bfc,0x34ff397d,0x36e83aa9,0xb8b2adc9,0xbbefbb59,0xb5bcba49,0x3bd730a6,0xb902382a,0xa452bb92,0x39373b7a,
  0xb9583874,0x3371bb16,0x34263c00,0xb982bafb,0x387a381a,0x347bbbe7,0xbb573a00,0x3b242776,0xbb8b324b,0x31093a25,0x3a58bb6f,0xbb4f2f8b,
  0xb86a3a6b,0x2ef53389,0x39c0b70a,0x3bfabb4c,0xaadeb232,0xb83034c3,0xbaee39bc,0xbbff3bb3,0x3bda3bc2,0x37b23a76,0xb5df2c06,0xbb9ab9d2,
  0xbb37b86f,0xba7abbf8,0x3029b654,0x3b7838f3,0x32633bea,0xba3dbad5,0x3c00352f,0xba1135b1,0xb9f4baa5,0x3bc8376f,0xbbba2311,0x39cdb7d2,
  0xbaa23ade,0x3baeb0f0,0xb65fb94a,0xb7373bff,0x3552bbd8,0xbbe6391f,0x38e035eb,0x3682bbf2,0xbaac38c7,0xbbf43bc6,0xb9903b2f,0xacce368d,
  0x3bfdbbd9,0x3ad1bba3,0x37feb994,0x26adb457,0x38a33b9a,0xb8dba452,0xbb83bbae,0x2a7ab86a,0x37423b78,0xbab6b426,0xb907bbe6,0x39aa2ade,
  0xb8403a11,0x341abb57,0x294d3bf4,0xb55ebbda,0xb93339cd,0x3889ba58,0xb7a63ad1,0x3625bb37,0xbbe33737,0x304239c0,0x3b42bb04,0xb95db263,
  0xbb9c3682,0xb2ad3aee,0x3bf5b8b2,0x1648b9f4,0xb3282cce,0xb80535df,0xb9e33902,0xbb3a3aa2,0xad0026ad,0xb1cf3029,0xb4873371,0xb61a3552,
  0xba85b4ff,0xba5cbc00,0x3581b47b,0x3bfd3aac,0xbb21b5bc,0xb85abbba,0x3a393109,0x39a63bfd,0xbac7b937,0x3bbc365f,0xbbfeaef5,0x3b89b219,
  0xba15b982,0x3a9738e0,0xbb07b830,0x3b6336e8,0x3153bb24,0xbbee3990,0x36bb37b2,0x39f0bbd7,0x34f3bb4f,0xbbd337fe,0xaec33a7a,0x3c00b958,
  0x3bccbbfa,0x3aebbb71,0x396bba3d,0x36ddb87a,0x3bfabbff,0x3bdebbef,0x3bacbbc8,0x3b65bb8b,0x3bc03911,0x38303b6a,0xb946ad65,0xbb4fbbd0,
  0x3a353bfd,0xb85f30f0,0xbb1ebbbc,0x35c8b5b1,0x38cc3b0d,0xba7ab99d,0x3b943759,0xbbffb19e,0xb4933b89,0x31e8bbc6,0xad333bee,0xa5e4bbff,
  0xb8153bf6,0x3bc8b63c,0xac38ba1d,0xbb783abd,0xbbf539f0,0x329438b7,0x3b9ebaeb,0xb676b68d,0xbbeb3ba9,0xbbe63c00,0xbb2c3b9f,0xb9cd3a90,
  0xb79b36dd,0xb884382a,0xb92e38db,0xb9c9397d,0x33eb3a31,0xbad1b602,0xba04bbf9,0x3682b2de,0xb90c2a7a,0xbab3bbe7,0x374eb41a,0x3b763b7a,
  0xba673790,0x38b2b9b3,0xb5233b1b,0x26adbbe0,0xbbabb55e,0x3bdd3389,0xbbf9b042,0x3bff2776,0xbae12e5f,0xb3713b5e,0x3bfcb929,0xb5bcb850,
  0xae91b95d,0xbbd43a76,0x34e73805,0x3b52bb4c,0x308db49f,0xb1091fdb,0xb71534db,0xb9823894,0x3b0abb3a,0x3a9bbad5,0x3a19ba5c,0x3986b9d2,
  0x2f8bb7e8,0x3bde3979,0x376f3b32,0xb9aab0d7,0x3bb83b24,0xb1223855,0xbbfdba3d,0xaa16b9a1,0x3bb3afef,0xbab63699,0x391fb94f,0xb6253ad8,
  0x30103bfa,0xb359bbdf,0x35463bae,0xb6d2bb68,0x38f3343e,0x3889bbff,0xbba3353a,0x96483a73,0xbaf13b9a,0x38ad32c6,0x39f8bbf4,0xb9eb9cb6,
  0xb7d238ea,0xb2ad35a5,0x2dc92ba7,0x361ab3a2,0xba543a11,0xbace3a93,0xbb353b04,0xbb873b60,0x3bf23af4,0x31cf39d6,0xbb16b6ff,0xb9a6bbe8,
  0xb4323737,0xbbe5baba,0x2b43b902,0x3bfe39af,0x34573bf0,0xb85abb4a,0x3a2539fc,0xbb63b825,0xbbef2cce,0x3bc9b1b6,0xbb8e347b,0x3b3db60e,
  0xba493bb7,0x3a97a81f,0x34c3bb90,0xbc0038bc,0xb7f3b4ff,0xba7e3bd2,0x39542ef5,0x3962bc00,0xbafb3a50,0xbbd33b7c,0xbbf83bfc,0xbb653bc5,
  0x38e5b937,0x3835b88e,0x36f4b7b2,0x356ab631,0xbb13bbe9,0x31e8b6f4,0x3bf239da,0x36763af1,0x3be83911,0x340e3ab0,0xbb7cb759,0xb72cbb73,
  0x2dfbbbc3,0x32943bfd,0xb7c8bb7f,0x39c93a54,0x38253b0d,0xb8d6ba9e,0x39793a1d,0xba0db98b,0x3ba5ba6f,0xb884b546,0xb8f83bff,0x3b76b432,
  0xb8bc3bf6,0x3ae8b27c,0x3699bb9f,0xbb98366b,0x391bb820,0x3ab3b9f8,0x3bb2bb47,0x3bffbbef,0xbbc53ba9,0xbbed3bdc,0xbbff3bf9,0xbbfb3c00,
  0x377ab0be,0x3bdd3b35,0x2f593974,0xbb52b7f3,0x30d73a31,0xbbbdb865,0xb5a5bb1b,0x3b2735d4,0x3bf733ba,0xbbd42b43,0x3afeb599,0xb98638e5,
  0xbad83790,0x3a60b87f,0xb9d63929,0x393cb9c5,0x34b738c1,0x3a9bbb8e,0xba45a884,0xb5c83bb8,0xba732e5f,0xb80a3bd6,0x3b4ab4db,0x350bbb54,
  0xba293adb,0xb85f3954,0xb46336a4,0x25e43010,0x33a2b49f,0x305bb201,0x281fad65,0xac9c251b,0x3f803f80,0x3f803f80,0x3f803f80,0x3f803f80,
  0x3f803f80,0x3f803f80,0x3f803f80,0x3f803f80,0x3f803f80,0x3f803f80,0x3f803f80,0x3f803f80,0x3f803f80,0x3f803f80,0x3f803f80,0x3f803f80,
  0x3f803f80,0x3f803f80,0x3f803f80,0x3f803f80,0x3f803f80,0x3f803f80,0x3f803f80,0x3f803f80,0x3f803f80,0x3f803f80,0x3f803f80,0x3f803f80,
  0x3f803f80,0x3f803f80,0x3f803f80,0x3f803f80,0x3f803f80,0x3f803f80,0x3f803f80,0x3f803f80,0x3f803f80,0x3f803f80,0x3f803f80,0x3f803f80,
  0x3f803f80,0x3f803f80,0x3f803f80,0x3f803f80,0x3f803f80,0x3f803f80,0x3f803f80,0x3f803f80,0x3f803f80,0x3f803f80,0x3f803f80,0x3f803f80,
  0x3f803f80,0x3f803f80,0x3f803f80,0x3f803f80,0x3f803f80,0x3f803f80,0x3f803f80,0x3f803f80,0x3f803f80,0x3f803f80,0x3f803f80,0x3f803f80,
  0x3f803f80,0x3f803f80,0x3f803f80,0x3f803f80,0x3f803f80,0x3f803f80,0x3f803f80,0x3f803f80,0x3f803f80,0x3f803f80,0x3f803f80,0x3f803f80,
  0x3f803f80,0x3f803f80,0x3f803f80,0x3f803f80,0x3f803f80,0x3f803f80,0x3f803f80,0x3f803f80,0x3f803f80,0x3f803f80,0x3f803f80,0x3f803f80,
  0x3f803f80,0x3f803f80,0x3f803f80,0x3f803f80,0x3f803f80,0x3f803f80,0x3f803f80,0x3f803f80,0x3f803f80,0x3f803f80,0x3f803f80,0x3f803f80,
  0x3f803f80,0x3f803f80,0x3f803f80,0x3f803f80,0x3f803f80,0x3f803f80,0x3f803f80,0x3f803f80,0x3f803f80,0x3f803f80,0x3f803f80,0x3f803f80,
  0x3f803f80,0x3f803f80,0x3f803f80,0x3f803f80,0x3f803f80,0x3f803f80,0x3f803f80,0x3f803f80,0x3f803f80,0x3f803f80,0x3f803f80,0x3f803f80,
  0x3f803f80,0x3f803f80,0x3f803f80,0x3f803f80,0x3f803f80,0x3f803f80,0x3f803f80,0x3f803f80,0x3f803f80,0x3f803f80,0x3f803f80,0x3f803f80,
  0x3f803f80,0x3f803f80,0x3f803f80,0x3f803f80,0x3f803f80,0x3f803f80,0x3f803f80,0x3f803f80,0x3f803f80,0x3f803f80,0x3f803f80,0x3f803f80,
  0x3f803f80,0x3f803f80,0x3f803f80,0x3f803f80,0x3f803f80,0x3f803f80,0x3f803f80,0x3f803f80,0x3f803f80,0x3f803f80,0x3f803f80,0x3f803f80,
  0x3f803f80,0x3f803f80,0x3f803f80,0x3f803f80,0x3f803f80,0x3f803f80,0x3f803f80,0x3f803f80,0x3f803f80,0x3f803f80,0x3f803f80,0x3f803f80,
  0x3f803f80,0x3f803f80,0x3f803f80,0x3f803f80,0x3f803f80,0x3f803f80,0x3f803f80,0x3f803f80,0x3f803f80,0x3f803f80,0x3f803f80,0x3f803f80,
  0x3f803f80,0x3f803f80,0x3f803f80,0x3f803f80,0x3f803f80,0x3f803f80,0x3f803f80,0x3f803f80,0x3f803f80,0x3f803f80,0x3f803f80,0x3f803f80,
  0x3f803f80,0x3f803f80,0x3f803f80,0x3f803f80,0x3f803f80,0x3f803f80,0x3f803f80,0x3f803f80,0x3f803f80,0x3f803f80,0x3f803f80,0x3f803f80,
  0x3f803f80,0x3f803f80,0x3f803f80,0x3f803f80,0x3f803f80,0x3f803f80,0x3f803f80,0x3f803f80,0x3f803f80,0x3f803f80,0x3f803f80,0x3f803f80,
  0x3f803f80,0x3f803f80,0x3f803f80,0x3f803f80,0x3f803f80,0x3f803f80,0x3f803f80,0x3f803f80,0x3f803f80,0x3f803f80,0x3f803f80,0x3f803f80,
  0x3f803f80,0x3f803f80,0x3f803f80,0x3f803f80,0x3f803f80,0x3f803f80,0x3f803f80,0x3f803f80,0x3f803f80,0x3f803f80,0x3f803f80,0x3f803f80,
  0x3f803f80,0x3f803f80,0x3f803f80,0x3f803f80,0x3f803f80,0x3f803f80,0x3f803f80,0x3f803f80,0x3f803f80,0x3f803f80,0x3f803f80,0x3f803f80,
  0x3f803f80,0x3f803f80,0x3f803f80,0x3f803f80,0x3f803f80,0x3f803f80,0x3f803f80,0x3f803f80,0x3f803f80,0x3f803f80,0x3f803f80,0x3f803f80,
  0x3f803f80,0x3f803f80,0x3f803f80,0x3f803f80,0x3f803f80,0x3f803f80,0x3f803f80,0x3f803f80,0x3f803f80,0x3f803f80,0x3f803f80,0x3f803f80,
  0x3f803f80,0x3f803f80,0x3f803f80,0x3f803f80,0x3f803f80,0x3f803f80,0x3f803f80,0x3f803f80,0x3f803f80,0x3f803f80,0x3f803f80,0x3f803f80,
  0x3f803f80,0x3f803f80,0x3f803f80,0x3f803f80,0x3f803f80,0x3f803f80,0x3f803f80,0x3f803f80,0x3f803f80,0x3f803f80,0x3f803f80,0x3f803f80,
  0x3f803f80,0x3f803f80,0x3f803f80,0x3f803f80,0x3f803f80,0x3f803f80,0x3f803f80,0x3f803f80,0x3f803f80,0x3f803f80,0x3f803f80,0x3f803f80,
  0x3f803f80,0x3f803f80,0x3f803f80,0x3f803f80,0x3f803f80,0x3f803f80,0x3f803f80,0x3f803f80,0x3f803f80,0x3f803f80,0x3f803f80,0x3f803f80,
  0x3f803f80,0x3f803f80,0x3f803f80,0x3f803f80,0x3f803f80,0x3f803f80,0x3f803f80,0x3f803f80,0x3f803f80,0x3f803f80,0x3f803f80,0x3f803f80,
  0x3f803f80,0x3f803f80,0x3f803f80,0x3f803f80,0x3f803f80,0x3f803f80,0x3f803f80,0x3f803f80,0x3f803f80,0x3f803f80,0x3f803f80,0x3f803f80,
  0x3f803f80,0x3f803f80,0x3f803f80,0x3f803f80,0x3f803f80,0x3f803f80,0x3f803f80,0x3f803f80,0x3f803f80,0x3f803f80,0x3f803f80,0x3f803f80,
  0x3f803f80,0x3f803f80,0x3f803f80,0x3f803f80,0x3f803f80,0x3f803f80,0x3f803f80,0x3f803f80,0x3f803f80,0x3f803f80,0x3f803f80,0x3f803f80,
  0x3f803f80,0x3f803f80,0x3f803f80,0x3f803f80,0x3f803f80,0x3f803f80,0x3f803f80,0x3f803f80,0x3f803f80,0x3f803f80,0x3f803f80,0x3f803f80,
  0x3f803f80,0x3f803f80,0x3f803f80,0x3f803f80,0x3f803f80,0x3f803f80,0x3f803f80,0x3f803f80,0x3f803f80,0x3f803f80,0x3f803f80,0x3f803f80,
  0x3f803f80,0x3f803f80,0x3f803f80,0x3f803f80,0x3f803f80,0x3f803f80,0x3f803f80,0x3f803f80,0x3f803f80,0x3f803f80,0x3f803f80,0x3f803f80,
  0x3f803f80,0x3f803f80,0x3f803f80,0x3f803f80,0x3f803f80,0x3f803f80,0x3f803f80,0x3f803f80,0x3f803f80,0x3f803f80,0x3f803f80,0x3f803f80,
  0x3f803f80,0x3f803f80,0x3f803f80,0x3f803f80,0x3f803f80,0x3f803f80,0x3f803f80,0x3f803f80,0x3f803f80,0x3f803f80,0x3f803f80,0x3f803f80,
  0x3f803f80,0x3f803f80,0x3f803f80,0x3f803f80,0x3f803f80,0x3f803f80,0x3f803f80,0x3f803f80,0x3f803f80,0x3f803f80,0x3f803f80,0x3f803f80,
  0x3f803f80,0x3f803f80,0x3f803f80,0x3f803f80,0x3f803f80,0x3f803f80,0x3f803f80,0x3f803f80,0x3f803f80,0x3f803f80,0x3f803f80,0x3f803f80,
  0x3f803f80,0x3f803f80,0x3f803f80,0x3f803f80,0x3f803f80,0x3f803f80,0x3f803f80,0x3f803f80,0x3f803f80,0x3f803f80,0x3f803f80,0x3f803f80,
  0x3f803f80,0x3f803f80,0x3f803f80,0x3f803f80,0x3f803f80,0x3f803f80,0x3f803f80,0x3f803f80,0x3f803f80,0x3f803f80,0x3f803f80,0x3f803f80,
  0x3f803f80,0x3f803f80,0x3f803f80,0x3f803f80,0x3f803f80,0x3f803f80,0x3f803f80,0x3f803f80,0x3f803f80,0x3f803f80,0x3f803f80,0x3f803f80,
  0x3f803f80,0x3f803f80,0x3f803f80,0x3f803f80,0x3f803f80,0x3f803f80,0x3f803f80,0x3f803f80,0x3f803f80,0x3f803f80,0x3f803f80,0x3f803f80,
  0x3f803f80,0x3f803f80,0x3f803f80,0x3f803f80,
};

__device__ __align__(128) float    g_part[16][8][2176];
__device__ __align__(128) float    g_kv[16][2176];
__device__ __align__(128) uint4    g_o[16 * 16 * 1024];
__device__ __align__(128) unsigned g_ocnt[16 * 32];
__device__ unsigned g_epoch[128];
#define GSTAMP(role, i) do {} while (0)
#define STAMP(role, i) do {} while (0)

constexpr int STAGE_BYTES = 57344;
constexpr int OFF_PK = 4 * 16384, OFF_V = 8 * 16384, OFF_H = 4 * 16384, OFF_VP = 9 * 16384, OFF_SPARE = 10 * 16384;
constexpr int OFF_XT = 172032, XT_STRIDE = 4112;
constexpr int OFF_BAR = 204928, OFF_EPOCH = OFF_BAR + 640, OFF_EX = OFF_BAR + 656, OFF_D = OFF_BAR + 672, OFF_SCALE = OFF_BAR + 704;
constexpr int OFF_F2F = 205824, OFF_F2I = 207872, OFF_F4 = 209920, OFF_ONES = 214016, OFF_KVB = 214016;
constexpr int OFF_STG = 219136, STG_STRIDE = 4352, SMEM_TOTAL = 232192;
enum { B_FULL1 = 0, B_EMPTY1 = 3, B_Q = 6, B_XRAW = 10, B_XT = 11, B_KV = 12, B_Y = 13, B_PKFREE = 14, B_AFREE = 15,
       B_STG = 18, B_ODONE = 24, B_XFREE = 25, B_FULL2 = 33, B_CONS2 = 49, B_COUNT = 62 };
__host__ __device__ constexpr int bar_count(int i) {
  return i < B_EMPTY1 ? 1 : i < B_Q ? 4 : i == B_XT ? 4 : i == B_KV ? 2 : i == B_Y ? 9 : i == B_PKFREE ? 4
       : (i >= B_AFREE && i < B_STG) ? 16 : i == B_ODONE ? 8 : (i >= B_XFREE && i < B_FULL2) ? 4
       : (i >= B_CONS2 && i <= B_CONS2 + 10) ? 4 : i >= B_CONS2 ? 2 : (i >= B_FULL2 && i < B_FULL2 + 7) ? 2 : 1;
}
__host__ __device__ constexpr uint64_t bar_counts(int r) {
  uint64_t v = 0;
  for (int w = 0; w < 12; w++) v |= (uint64_t)(bar_count(12 * r + w) - 1) << (4 * w);
  return v;
}
constexpr uint64_t SLOT_A = 0x9645796457964594ull;
constexpr uint64_t SLOT_B = 0x1032810328103276ull;
constexpr int SPIN_LIMIT = 1 << 22;
#define PKV CU_TENSOR_MAP_L2_PROMOTION_L2_128B
#define BPRE B_KV
#define PFD 3
#define PD1 500
#define PD2 300
#define E1C 2
#define OSP 4
#define QPF 4
#define HSTART 1500
#define PACE 1050
#define OC 1

__device__ __forceinline__ uint32_t smem_u32(const void* p) { return (uint32_t)__cvta_generic_to_shared(p); }
__device__ __forceinline__ void wg_fence() { asm volatile("wgmma.fence.sync.aligned;" ::: "memory"); }
__device__ __forceinline__ void wg_commit() { asm volatile("wgmma.commit_group.sync.aligned;" ::: "memory"); }
template <int N> __device__ __forceinline__ void wg_wait() { asm volatile("wgmma.wait_group.sync.aligned %0;" ::"n"(N) : "memory"); }
template <int N> __device__ __forceinline__ void keep(float (&d)[N]) {
#pragma unroll
  for (int i = 0; i < N; i++) asm volatile("" : "+f"(d[i])::"memory");
}
__device__ __forceinline__ uint64_t mkdesc(uint32_t addr, uint32_t lbo, uint32_t sbo, uint32_t swz) {
  uint32_t lo = ((addr & 0x3FFFF) >> 4) | ((lbo >> 4) << 16), hi = (sbo >> 4) | (swz << 30);
  return ((uint64_t)hi << 32) | lo;
}
__device__ __forceinline__ void mbar_init(uint32_t bar, int cnt) { asm volatile("mbarrier.init.shared::cta.b64 [%0], %1;" ::"r"(bar), "r"(cnt)); }
__device__ __forceinline__ void mbar_expect(uint32_t bar, int bytes) { asm volatile("mbarrier.arrive.expect_tx.shared::cta.b64 _, [%0], %1;" ::"r"(bar), "r"(bytes) : "memory"); }
__device__ __forceinline__ void mbar_arrive(uint32_t bar) { asm volatile("mbarrier.arrive.shared::cta.b64 _, [%0];" ::"r"(bar) : "memory"); }
__device__ __forceinline__ void mbar_arrive_cl(uint32_t bar, uint32_t cta) {
  asm volatile("{\n.reg .b32 r;\nmapa.shared::cluster.u32 r, %0, %1;\nmbarrier.arrive.shared::cluster.b64 _, [r];\n}\n" ::"r"(bar), "r"(cta) : "memory");
}
__device__ __forceinline__ void mbar_wait(uint32_t bar, uint32_t parity) {
  asm volatile("{\n.reg .pred p;\n.reg .u32 n;\nmov.u32 n, 0;\n"
               "W_%=:\nmbarrier.try_wait.parity.shared::cta.b64 p, [%0], %1;\n@p bra D_%=;\n"
               "add.u32 n, n, 1;\nsetp.lt.u32 p, n, %2;\n@p bra W_%=;\ntrap;\nD_%=:\n}\n" ::"r"(bar), "r"(parity), "n"(SPIN_LIMIT) : "memory");
}
__device__ __forceinline__ void fence_async() { asm volatile("fence.proxy.async.shared::cta;" ::: "memory"); }
__device__ __forceinline__ void bar_sync(int id) { asm volatile("bar.sync %0, 128;" ::"r"(id) : "memory"); }
__device__ __forceinline__ void tma2d(uint32_t dst, const CUtensorMap* m, int c0, int c1, uint32_t bar) {
  asm volatile("cp.async.bulk.tensor.2d.shared::cluster.global.mbarrier::complete_tx::bytes [%0], [%1, {%3, %4}], [%2];"
               ::"r"(dst), "l"(m), "r"(bar), "r"(c0), "r"(c1) : "memory");
}
__device__ __forceinline__ void tma2d_mc(uint32_t dst, const CUtensorMap* m, int c0, int c1, uint32_t bar) {
  asm volatile("cp.async.bulk.tensor.2d.shared::cluster.global.mbarrier::complete_tx::bytes.multicast::cluster [%0], [%1, {%3, %4}], [%2], %5;"
               ::"r"(dst), "l"(m), "r"(bar), "r"(c0), "r"(c1), "h"((uint16_t)3) : "memory");
}
__device__ __forceinline__ void tma3d(uint32_t dst, const CUtensorMap* m, int c0, int c1, int c2, uint32_t bar) {
  asm volatile("cp.async.bulk.tensor.3d.shared::cluster.global.mbarrier::complete_tx::bytes [%0], [%1, {%3, %4, %5}], [%2];"
               ::"r"(dst), "l"(m), "r"(bar), "r"(c0), "r"(c1), "r"(c2) : "memory");
}
__device__ __forceinline__ void bulk_ld(uint32_t dst, const void* src, int bytes, uint32_t bar) {
  asm volatile("cp.async.bulk.shared::cluster.global.mbarrier::complete_tx::bytes [%0], [%1], %2, [%3];" ::"r"(dst), "l"(src), "r"(bytes), "r"(bar) : "memory");
}
__device__ __forceinline__ void bulk_ld_mc(uint32_t dst, const void* src, int bytes, uint32_t bar) {
  asm volatile("cp.async.bulk.shared::cluster.global.mbarrier::complete_tx::bytes.multicast::cluster [%0], [%1], %2, [%3], %4;"
               ::"r"(dst), "l"(src), "r"(bytes), "r"(bar), "h"((uint16_t)3) : "memory");
}
__device__ __forceinline__ void tma2d_st(const CUtensorMap* m, uint32_t src, int c0, int c1) {
  asm volatile("cp.async.bulk.tensor.2d.global.shared::cta.bulk_group [%0, {%2, %3}], [%1];" ::"l"(m), "r"(src), "r"(c0), "r"(c1) : "memory");
}
__device__ __forceinline__ void pf_l2(const void* p, int bytes) { asm volatile("cp.async.bulk.prefetch.L2.global [%0], %1;" ::"l"(p), "r"(bytes) : "memory"); }
__device__ __forceinline__ void pf_t2d(const CUtensorMap* m, int c0, int c1) {
  asm volatile("cp.async.bulk.prefetch.tensor.2d.L2.global [%0, {%1, %2}];" ::"l"(m), "r"(c0), "r"(c1) : "memory");
}
__device__ __forceinline__ void pf_t3d(const CUtensorMap* m, int c0, int c1, int c2) {
  asm volatile("cp.async.bulk.prefetch.tensor.3d.L2.global [%0, {%1, %2, %3}];" ::"l"(m), "r"(c0), "r"(c1), "r"(c2) : "memory");
}
__device__ __forceinline__ void ldsm4(uint32_t (&r)[4], uint32_t a) {
  asm volatile("ldmatrix.sync.aligned.m8n8.x4.shared.b16 {%0,%1,%2,%3}, [%4];" : "=r"(r[0]), "=r"(r[1]), "=r"(r[2]), "=r"(r[3]) : "r"(a) : "memory");
}
__device__ __forceinline__ void ldsm4t(uint32_t (&r)[4], uint32_t a) {
  asm volatile("ldmatrix.sync.aligned.m8n8.x4.trans.shared.b16 {%0,%1,%2,%3}, [%4];" : "=r"(r[0]), "=r"(r[1]), "=r"(r[2]), "=r"(r[3]) : "r"(a) : "memory");
}
__device__ __forceinline__ void stsm4(uint32_t a, uint32_t r0, uint32_t r1, uint32_t r2, uint32_t r3) {
  asm volatile("stmatrix.sync.aligned.m8n8.x4.shared.b16 [%0], {%1,%2,%3,%4};" ::"r"(a), "r"(r0), "r"(r1), "r"(r2), "r"(r3) : "memory");
}
__device__ __forceinline__ uint32_t pk2(float lo, float hi) { uint32_t r; asm("cvt.rn.bf16x2.f32 %0, %1, %2;" : "=r"(r) : "f"(hi), "f"(lo)); return r; }
__device__ __forceinline__ uint32_t hmul(uint32_t a, uint32_t b) { uint32_t r; asm("mul.rn.bf16x2 %0, %1, %2;" : "=r"(r) : "r"(a), "r"(b)); return r; }
__device__ __forceinline__ uint32_t hadd(uint32_t a, uint32_t b) { uint32_t r; asm("add.rn.bf16x2 %0, %1, %2;" : "=r"(r) : "r"(a), "r"(b)); return r; }
__device__ __forceinline__ uint32_t hmax(uint32_t a, uint32_t b) { uint32_t r; asm("max.bf16x2 %0, %1, %2;" : "=r"(r) : "r"(a), "r"(b)); return r; }
__device__ __forceinline__ uint32_t hmin(uint32_t a, uint32_t b) { uint32_t r; asm("min.bf16x2 %0, %1, %2;" : "=r"(r) : "r"(a), "r"(b)); return r; }
__device__ __forceinline__ uint32_t hmaxabs(uint32_t a, uint32_t b) { uint32_t r; asm("max.xorsign.abs.bf16x2 %0, %1, %2;" : "=r"(r) : "r"(a), "r"(b)); return r; }
__device__ __forceinline__ float ex2(float x) { float r; asm("ex2.approx.ftz.f32 %0, %1;" : "=f"(r) : "f"(x)); return r; }
__device__ __forceinline__ float rcp_fast(float x) { float r; asm("rcp.approx.ftz.f32 %0, %1;" : "=f"(r) : "f"(x)); return r; }
__device__ __forceinline__ uint32_t phi2(float lo, float hi) {
  uint32_t t;
  asm("cvt.rn.relu.bf16x2.f32 %0, %1, %2;" : "=r"(t) : "f"(hi), "f"(lo));
  const uint32_t e = pk2(ex2(lo * 1.4426950408889634f), ex2(hi * 1.4426950408889634f));
  return hadd(hadd(t, hmin(e, 0x3F803F80u)), 0x35863586u);
}
__device__ __forceinline__ bool opaque_true() { uint32_t v; asm volatile("mov.u32 %0, %%nctaid.y;" : "=r"(v)); return v != 0; }
__device__ __forceinline__ int normalise(uint32_t (&v)[32], float fd) {
  const float f0 = fd + __uint_as_float(v[0] << 16);
  uint32_t m[4] = {hmaxabs(__float_as_uint(f0) >> 16, v[0]), v[1], v[2], v[3]};
#pragma unroll
  for (int i = 4; i < 32; i++) m[i & 3] = hmaxabs(m[i & 3], v[i]);
  m[0] = hmaxabs(hmaxabs(m[0], m[1]), hmaxabs(m[2], m[3]));
  const int e = min(max((int)(__reduce_max_sync(~0u, max(m[0] & 0x7FFFu, (m[0] >> 16) & 0x7FFFu)) >> 7), 1), 253);
  if (e > 141) {
#pragma unroll
    for (int i = 0; i < 32; i++) v[i] = hmul(v[i], 0x07000700u);
  }
  const uint32_t sc = (e > 141 ? 255 - e : 142 - e) * 0x00800080u;
#pragma unroll
  for (int i = 0; i < 32; i++) {
    const uint32_t a = hmul(v[i], sc);
    v[i] = (a & 0x0FFF0FFFu) * 7 + a;
  }
  v[0] = __byte_perm(v[0], __half_as_ushort(__float2half_rn(f0 * __uint_as_float((254 - e) << 23))), 0x3254);
  return e;
}
__device__ __forceinline__ void poll_ge(const unsigned* p, unsigned target) {
#pragma unroll 1
  for (int n = 0; n < SPIN_LIMIT; n++) {
    unsigned v;
    asm volatile("ld.relaxed.gpu.global.u32 %0, [%1];" : "=r"(v) : "l"(p) : "memory");
    if ((int)(v - target) >= 0) { asm volatile("fence.acquire.gpu;" ::: "memory"); return; }
  }
  __trap();
}

__device__ __forceinline__ bool elect_one() {
  uint32_t p;
  asm volatile("{\n.reg .pred p;\nelect.sync _|p, 0xffffffff;\nselp.u32 %0, 1, 0, p;\n}\n" : "=r"(p));
  return p;
}
__device__ __forceinline__ uint32_t mapa(uint32_t a, uint32_t cta) { uint32_t r; asm("mapa.shared::cluster.u32 %0, %1, %2;" : "=r"(r) : "r"(a), "r"(cta)); return r; }
__device__ __forceinline__ void st_async(uint32_t a, uint32_t v, uint32_t bar) {
  asm volatile("st.async.weak.shared::cluster.mbarrier::complete_tx::bytes.b32 [%0], %1, [%2];" ::"r"(a), "r"(v), "r"(bar) : "memory");
}
__device__ __forceinline__ void st_async4(uint32_t a, uint32_t x, uint32_t y, uint32_t z, uint32_t w, uint32_t bar) {
  asm volatile("st.async.weak.shared::cluster.mbarrier::complete_tx::bytes.v4.b32 [%0], {%1,%2,%3,%4}, [%5];" ::"r"(a), "r"(x), "r"(y), "r"(z), "r"(w), "r"(bar) : "memory");
}
__device__ __forceinline__ void tma3d_st(const CUtensorMap* m, uint32_t src, int c0, int c1, int c2) {
  asm volatile("cp.async.bulk.tensor.3d.global.shared::cta.bulk_group [%0, {%2, %3, %4}], [%1];" ::"l"(m), "r"(src), "r"(c0), "r"(c1), "r"(c2) : "memory");
}
__device__ __forceinline__ uint4 ld_rlx4(const void* p) {
  uint4 v;
  asm volatile("{\n.reg .b128 t;\n.reg .b64 a, b;\nld.relaxed.gpu.global.b128 t, [%4];\nmov.b128 {a, b}, t;\nmov.b64 {%0, %1}, a;\nmov.b64 {%2, %3}, b;\n}\n"
               : "=r"(v.x), "=r"(v.y), "=r"(v.z), "=r"(v.w) : "l"(p) : "memory");
  return v;
}
__device__ __forceinline__ void st_tag4(void* p, float a, float b, float c, float d, uint32_t tag) {
  asm volatile("{\n.reg .b128 t;\n.reg .b64 a, b;\nmov.b64 a, {%1, %2};\nmov.b64 b, {%3, %4};\nmov.b128 t, {a, b};\nst.relaxed.gpu.global.b128 [%0], t;\n}\n"
               ::"l"(p), "r"((__float_as_uint(a) & ~1u) | tag), "f"(b), "f"(c), "f"(d) : "memory");
}
__device__ __forceinline__ uint32_t stale8(const uint4 (&f)[8], uint32_t tag) {
  uint32_t r[4];
#pragma unroll
  for (int i = 0; i < 4; i++) asm("lop3.b32 %0, %1, %2, %3, 0x7E;" : "=r"(r[i]) : "r"(f[2 * i].x), "r"(f[2 * i + 1].x), "r"(tag));
  asm("lop3.b32 %0, %0, %1, %2, 0xFE;" : "+r"(r[0]) : "r"(r[1]), "r"(r[2]));
  return r[0] | r[3];
}

struct ConvC { uint32_t a1[2][4], wa[2], wb[2], sg; };
__device__ __forceinline__ uint64_t dsc(uint32_t lo, uint32_t hi) { return ((uint64_t)hi << 32) | lo; }
__device__ __forceinline__ uint32_t hfma(uint32_t a, uint32_t b, uint32_t c) { uint32_t r; asm("fma.rn.f16x2 %0, %1, %2, %3;" : "=r"(r) : "r"(a), "r"(b), "r"(c)); return r; }
__device__ __forceinline__ uint32_t hfnma(uint32_t a, uint32_t b, uint32_t c) { uint32_t r; asm("{.reg .b32 n; neg.f16x2 n, %1; fma.rn.f16x2 %0, n, %2, %3;}" : "=r"(r) : "r"(a), "r"(b), "r"(c)); return r; }
__device__ __forceinline__ uint32_t hmul16(uint32_t a, uint32_t b) { uint32_t r; asm("mul.rn.f16x2 %0, %1, %2;" : "=r"(r) : "r"(a), "r"(b)); return r; }
template <int N> __device__ __forceinline__ void keepu(uint32_t (&d)[N]) {
#pragma unroll
  for (int i = 0; i < N; i++) asm volatile("" : "+r"(d[i])::"memory");
}
__device__ __forceinline__ void conv_m1(const ConvC& K, uint32_t (&u)[16], uint32_t l) {
  wg_fence();
#pragma unroll
  for (int s = 0; s < 2; s++) wgmma_hrs_n64<1>(u, K.a1[s][0], K.a1[s][1], K.a1[s][2], K.a1[s][3], dsc(l + s * 16, 32), s);
  wg_commit();
}
__device__ __forceinline__ void conv_s2(const ConvC& K, uint32_t (&u)[16], uint32_t (&Z)[2][8], uint32_t dfl) {
  uint32_t fr[8], fi[8];
#pragma unroll
  for (int c = 0; c < 8; c++) {
    const uint32_t r = hfma(K.wa[c & 1], u[2 * c + 1], u[2 * c]);
    fi[c] = hfma(K.wb[c & 1], r, u[2 * c + 1]);
    fr[c] = hfma(K.wa[c & 1], fi[c], r);
  }
  wg_fence();
#pragma unroll
  for (int p = 0; p < 2; p++) {
    wgmma_hrs_n32<0>(Z[p], fr[4 * p], fr[4 * p + 2], fr[4 * p + 1], fr[4 * p + 3], dsc(dfl, 32), 0);
    wgmma_hrs_n32<0>(Z[p], fi[4 * p], fi[4 * p + 2], fi[4 * p + 1], fi[4 * p + 3], dsc(dfl + 16, 32), 1);
  }
  wg_commit();
}
__device__ __forceinline__ void conv_win(const ConvC& K, uint32_t (&X)[2][8]) {
#pragma unroll
  for (int b = 3; b >= 1; b--)
#pragma unroll
    for (int c = 0; c < 2; c++) {
      uint32_t& xr = X[b >> 1][2 * c + (b & 1)]; uint32_t& xi = X[b >> 1][4 + 2 * c + (b & 1)];
      xr = hfnma(K.sg, X[(b - 1) >> 1][4 + 2 * c + ((b - 1) & 1)], xr);
      xi = hfma(K.sg, X[(b - 1) >> 1][2 * c + ((b - 1) & 1)], xi);
    }
}
template <int p>
__device__ __forceinline__ void conv_pw(uint32_t (&X)[2][8], uint32_t (&H)[2][8], uint32_t (&V)[8], uint32_t dil) {
  uint32_t pr[2][2], pi[2][2];
#pragma unroll
  for (int jj = 0; jj < 2; jj++)
#pragma unroll
    for (int c = 0; c < 2; c++) {
      const int j = 2 * p + jj;
      uint32_t sr = 0, si = 0;
#pragma unroll
      for (int a = 0; a <= j; a++) {
        const int b = j - a;
        const uint32_t hr = H[a >> 1][2 * c + (a & 1)], hi = H[a >> 1][4 + 2 * c + (a & 1)];
        const uint32_t xr = X[b >> 1][2 * c + (b & 1)], xi = X[b >> 1][4 + 2 * c + (b & 1)];
        sr = a == 0 ? hmul16(hr, xr) : hfma(hr, xr, sr);
        si = a == 0 ? hmul16(hr, xi) : hfma(hr, xi, si);
        sr = hfnma(hi, xi, sr);
        si = hfma(hi, xr, si);
      }
      pr[jj][c] = sr; pi[jj][c] = si;
    }
  wg_fence();
  wgmma_hrs_n32<0>(V, pr[0][0], pr[1][0], pr[0][1], pr[1][1], dsc(dil, 32), 0);
  wgmma_hrs_n32<0>(V, pi[0][0], pi[1][0], pi[0][1], pi[1][1], dsc(dil + 16, 32), 1);
  wg_commit();
}
template <int p>
__device__ __forceinline__ void conv_it(const ConvC& K, uint32_t (&V)[8], uint32_t vst) {
#pragma unroll
  for (int jj = 0; jj < 2; jj++) {
    uint32_t wr[2], wi[2];
#pragma unroll
    for (int c = 0; c < 2; c++) {
      const uint32_t r = hfnma(K.wa[c], V[4 + 2 * c + jj], V[2 * c + jj]);
      wi[c] = hfnma(K.wb[c], r, V[4 + 2 * c + jj]);
      wr[c] = hfnma(K.wa[c], wi[c], r);
    }
    stsm4(vst + (2 * p + jj) * 2048, wr[0], wr[1], wi[0], wi[1]);
  }
}
__device__ __forceinline__ void conv_m4(uint32_t (&y)[8], uint32_t (&a)[4][4], uint32_t d4l) {
  wg_fence();
#pragma unroll
  for (int s = 0; s < 4; s++) wgmma_hrs_n32<0>(y, a[s][0], a[s][1], a[s][2], a[s][3], dsc(d4l + s * 16, 64), s);
  wg_commit();
}

struct Params {
  CUtensorMap tmX, tmW, tmWo, tmK, tmV, tmQ, tmOA, tmOB;
  const __nv_bfloat16 *shift_k, *h, *D, *x, *w, *wo, *q;
};

__global__ void __cluster_dims__(2, 1, 1) __launch_bounds__(384, 1) fused_kernel(const __grid_constant__ Params P) {
  extern __shared__ __align__(1024) uint8_t smem[];
  const uint32_t sb = smem_u32(smem);
  const uint32_t bars = sb + OFF_BAR;
  const int tid = threadIdx.x, lane = tid & 31;
  const int warp = __shfl_sync(~0u, tid >> 5, 0);
  const int rank = blockIdx.x & 1, cl = blockIdx.x >> 1;
  const int mb = cl >> 3, hq = cl & 7;
  const int hp = 2 * hq + rank;
  const int rb = 2 * mb + (hq >> 2), cb = hq & 3;
#define BAR(i) (bars + 8 * (i))

  if (tid == 0) { STAMP(0, 0); GSTAMP(0, 30); }
  if (lane == 0) {
#pragma unroll
    for (int r = 0; r < 6; r++)
      if (r < 5 || warp < B_COUNT - 60) mbar_init(BAR(12 * r + warp), ((uint32_t)(bar_counts(r) >> (4 * warp)) & 15) + 1);
    asm volatile("fence.mbarrier_init.release.cluster;" ::: "memory");
  }
  asm volatile("barrier.cluster.arrive.relaxed.aligned;\nbarrier.cluster.wait.aligned;" ::: "memory");

  if (warp < 8) {
    asm volatile("setmaxnreg.inc.sync.aligned.u32 224;");
    const int wg = warp >> 2, w = warp & 3, g = lane >> 2, q = lane & 3, t = tid & 127;
    const bool elect = (t == 0);
    const uint32_t s16 = (sb & 0x3FFFF) >> 4;
    constexpr uint32_t SW128 = 64 | (1u << 30);
    uint32_t pq[2][16], v[32];
    ConvC K;
    {
      float acc[2][96];
      int st = 0, ph = 0;
#pragma unroll 1
      for (int kb = 0; kb < 16; kb++) {
        mbar_wait(BAR(B_FULL1 + st), ph);
        if (kb == 0 && elect) { STAMP(wg, 1); GSTAMP(wg, 26); }
        if (kb == 8 && elect) { STAMP(wg, 16); GSTAMP(wg, 25); }
        if (tid == 0) STAMP(2, 8 + kb);
        const uint32_t da = s16 + st * (STAGE_BYTES >> 4) + wg * 1024 + (1 << 16);
        const uint32_t db = s16 + st * (STAGE_BYTES >> 4) + 2048 + (512 << 16);
        wg_fence();
#pragma unroll
        for (int ks = 0; ks < 4; ks++) {
          wgmma_ss_n192<0, 1>(acc[0], dsc(da + ks * 2, SW128), dsc(db + ks * 128, SW128), (kb | ks) != 0);
          wgmma_ss_n192<0, 1>(acc[1], dsc(da + 512 + ks * 2, SW128), dsc(db + ks * 128, SW128), (kb | ks) != 0);
        }
        wg_commit();
        wg_wait<1>();
        if (kb > 0 && t < 2) mbar_arrive_cl(BAR(B_EMPTY1 + (st == 0 ? 2 : st - 1)), t);
        if (++st == 3) { st = 0; ph ^= 1; }
      }
      wg_wait<0>();
      keep(acc[0]); keep(acc[1]);
      if (t < 2) mbar_arrive_cl(BAR(B_EMPTY1 + 0), t);
      if (elect) { STAMP(wg, 2); GSTAMP(wg, 27); }
      mbar_wait(BAR(B_EMPTY1 + 2), 0);
      const uint32_t lrow = sb + wg * 16384 + (16 * w + 8 * ((lane >> 3) & 1) + (lane & 7)) * 128 + (((lane >> 4) ^ (lane & 7)) << 4);
#pragma unroll
      for (int i = 0; i < 8; i += E1C)
        if (opaque_true()) {
#pragma unroll
          for (int j = i; j < i + E1C; j++) {
            const float* a = &acc[j >> 2][32 + 8 * (j & 3)];
            const float* b = a + 32;
            const uint32_t o = (lrow ^ ((j & 3) * 32)) + (j >> 2) * 8192;
            stsm4(o + OFF_V, pk2(b[0], b[1]), pk2(b[2], b[3]), pk2(b[4], b[5]), pk2(b[6], b[7]));
            stsm4(o + OFF_PK, phi2(a[0], a[1]), phi2(a[2], a[3]), phi2(a[4], a[5]), phi2(a[6], a[7]));
          }
        }
      fence_async();
      mbar_wait(BAR(B_XT), 0);
#define LOAD_CONV_INPUTS() do { \
        const uint4* ct = (const uint4*)c_thr + t; \
        const uint4* hp4 = (const uint4*)(P.h + (blockIdx.x * 8 + warp) * 2048) + ((lane & 15) * 2 + (lane >> 4)); \
        _Pragma("unroll") for (int i = 0; i < 8; i++) { const uint4 u = __ldg(hp4 + i * 32); v[4 * i] = u.x; v[4 * i + 1] = u.y; v[4 * i + 2] = u.z; v[4 * i + 3] = u.w; } \
        _Pragma("unroll") for (int s = 0; s < 2; s++) { const uint4 u = __ldg(ct + s * 128); K.a1[s][0] = u.x; K.a1[s][1] = u.y; K.a1[s][2] = u.z; K.a1[s][3] = u.w; } \
        const uint4 u = __ldg(ct + 2 * 128); K.wa[0] = u.x; K.wa[1] = u.y; K.wb[0] = u.z; K.wb[1] = u.w; } while (0)
      K.sg = (lane & 4) ? 0xBC00BC00u : 0x3C003C00u;
      if (wg == 0) {
        asm volatile("bar.sync 3, 256;" ::: "memory");
        if (elect) STAMP(wg, 3);
        float kva[36];
        wg_fence();
#pragma unroll
        for (int ks = 0; ks < 16; ks++)
          wgmma_ss_n72<1, 1>(kva, dsc(s16 + (OFF_PK >> 4) + ks * 128 + (1 << 16), SW128),
                             dsc(s16 + (OFF_V >> 4) + ks * 128 + (((OFF_ONES - OFF_V - ks * 2048) >> 4) << 16), SW128), ks != 0);
        wg_commit();
        LOAD_CONV_INPUTS();
        const uint32_t tag = ~*(volatile unsigned*)(smem + OFF_EPOCH) & 1;
        float* dst = &g_part[hp][mb][0];
        wg_wait<0>();
        keep(kva);
#pragma unroll
        for (int c = 0; c < 4; c++)
          st_tag4(dst + (c * 128 + t) * 4, w < 2 ? kva[4 * c] : kva[16 + 4 * c], w < 2 ? kva[4 * c + 1] : kva[17 + 4 * c],
                  w < 2 ? kva[4 * c + 2] : kva[18 + 4 * c], w < 2 ? kva[4 * c + 3] : kva[19 + 4 * c], tag);
        {
          const float z2 = __shfl_down_sync(~0u, kva[32], 4), z3 = __shfl_down_sync(~0u, kva[34], 4);
          if (!(lane & 7)) st_tag4(dst + 2048 + 16 * w + 2 * g, kva[32], kva[34], z2, z3, tag);
        }
        if (lane == 0) mbar_arrive(BAR(B_PKFREE));
      } else {
        asm volatile("bar.arrive 3, 256;" ::: "memory");
        LOAD_CONV_INPUTS();
      }
      if (elect) STAMP(wg, 4);
#pragma unroll
      for (int mt = 0; mt < 2; mt++)
#pragma unroll
        for (int i = 0; i < 16; i++) pq[mt][i] = phi2(acc[mt][2 * i], acc[mt][2 * i + 1]);
      keepu(pq[0]); keepu(pq[1]);
    }
    if (elect) STAMP(wg, 17);
    {
      const int e = normalise(v, lane == 0 ? *(const float*)(smem + OFF_D + 4 * warp) : 0.f);
      uint8_t* dst = smem + OFF_H + (w & 2) * 8192 + wg * 8192 + (w & 1) * 4096 + (lane >> 4) * 512 + (lane & 15) * 16;
      mbar_wait(BAR(B_PKFREE), 0);
#pragma unroll
      for (int i = 0; i < 8; i++)
        *(uint4*)(dst + (i >> 1) * 1024 + (i & 1) * 256) = make_uint4(v[4 * i], v[4 * i + 1], v[4 * i + 2], v[4 * i + 3]);
      if (lane < 2) st_async(mapa(sb + OFF_SCALE + (8 * rank + warp) * 4, lane), min(max(e + smem[OFF_EX + warp] - 124, 1), 254) << 23, mapa(BAR(B_Y), lane));
      fence_async();
      bar_sync(1 + wg);
    }
    if (elect) STAMP(wg, 5);
    {
      const uint32_t dfl = s16 + (OFF_F2F >> 4) + (8 << 16), dil = s16 + (OFF_F2I >> 4) + (8 << 16), d4l = s16 + (OFF_F4 >> 4) + (8 << 16);
      const uint32_t xl = s16 + (OFF_XT >> 4) + 4 * wg * (XT_STRIDE >> 4) + (8 << 16);
      const uint32_t hl = s16 + (OFF_H >> 4) + wg * 512 + (8 << 16);
      uint32_t vst = sb + wg * 8192 + w * 512 + lane * 16, vld = sb + wg * 8192 + w * 2048 + lane * 16;
      uint32_t ya = mapa(sb + OFF_XT + 4 * wg * XT_STRIDE + (2 * rank + (w & 1)) * 1024 + lane * 16, w >> 1);
      const uint32_t ybar = mapa(BAR(B_Y), w >> 1);
      asm volatile("" : "+r"(vst), "+r"(vld), "+r"(ya));
      uint32_t ux[16], uh[16], X[4][2][8], H[4][2][8], V0[8], V1[8], y[8], a[4][4];
#define YOUT(i) do { mbar_wait(BAR(B_XFREE + 4 * wg + (i)), 0); \
        st_async4(ya + (i) * XT_STRIDE, y[0], y[2], y[4], y[6], ybar); \
        st_async4(ya + (i) * XT_STRIDE + 512, y[1], y[3], y[5], y[7], ybar); } while (0)
      conv_m1(K, ux, xl);
      conv_m1(K, uh, hl);
      wg_wait<1>(); keepu(ux);
      if (lane == 0) mbar_arrive_cl(BAR(B_XFREE + 4 * wg), rank ^ 1);
      conv_s2(K, ux, X[0], dfl);
      wg_wait<1>(); keepu(uh);
      conv_s2(K, uh, H[0], dfl);
#pragma unroll
      for (int i = 0; i < 4; i++) {
        const bool nx = i < 3;
        const int n = nx ? i + 1 : i;
        const uint32_t vo = (i & 1) ? OFF_H + (i >> 1) * 16384 : OFF_VP;
        float oa[4][20];
        uint4 ov[8];
#define OSTORE(m) do { _Pragma("unroll") for (int r = 0; r < 2; r++) \
          asm volatile("st.global.cg.v4.u32 [%0], {%1,%2,%3,%4};" ::"l"(g_o + ((2 * mb + wg) * 16 + hp) * 1024 + (16 * w + g + 64 * ((m) >> 1) + 8 * r) * 8 + ((4 * ((m) & 1) + q) ^ g)), \
                       "r"(ov[2 * (m) + r].x), "r"(ov[2 * (m) + r].y), "r"(ov[2 * (m) + r].z), "r"(ov[2 * (m) + r].w) : "memory"); \
          if ((m) == 3) { __syncwarp(); if (lane == 0) mbar_arrive(BAR(B_ODONE)); if (elect) STAMP(wg, 10); } } while (0)
        if (i == OC) {
          if (elect) STAMP(wg, 8);
          mbar_wait(BAR(B_KV), 0);
          if (elect) STAMP(wg, 9);
          wg_wait<0>();
          wg_fence();
#pragma unroll
          for (int m = 0; m < 8; m++) {
            const uint32_t* p = &pq[m >> 2][4 * (m & 3)];
            wgmma_rs_n40<1>(oa[m >> 1], p[0], p[1], p[2], p[3], dsc(s16 + (OFF_KVB >> 4) + ((m >> 1) & 1) * 160 + (m & 1) * 16 + (8 << 16), 32), m & 1);
          }
          wg_commit();
        }
        if (nx) {
          conv_m1(K, ux, xl + n * (XT_STRIDE >> 4));
          conv_m1(K, uh, hl + (n >> 1) * 1024 + (n & 1) * 256);
        }
        if (i == OC) { if (nx) wg_wait<2>(); else wg_wait<0>(); }
        else if (nx) { if (i > 0) wg_wait<3>(); else wg_wait<2>(); }
        else wg_wait<1>();
        if (i == OC) {
#pragma unroll
          for (int m = 0; m < 4; m++) {
            float (&o)[20] = oa[m];
            keep(o);
            const uint32_t den = hadd(pk2(o[16], o[18]), 0x35863586u);
#pragma unroll
            for (int r = 0; r < 2; r++) {
              const float ri = rcp_fast(__uint_as_float(r ? (den & 0xFFFF0000u) : (den << 16)));
              uint4 u;
              u.x = pk2(o[2 * r] * ri, o[2 * r + 1] * ri);
              u.y = pk2(o[4 + 2 * r] * ri, o[5 + 2 * r] * ri);
              u.z = pk2(o[8 + 2 * r] * ri, o[9 + 2 * r] * ri);
              u.w = pk2(o[12 + 2 * r] * ri, o[13 + 2 * r] * ri);
              ov[2 * m + r] = u;
            }
            if (m < OSP) OSTORE(m);
          }
        }
        keepu(X[i][0]); keepu(X[i][1]); keepu(H[i][0]); keepu(H[i][1]);
        conv_win(K, X[i]);
        if (i == OC && OSP < 2) OSTORE(1);
        conv_pw<0>(X[i], H[i], V0, dil);
        if (i == OC && OSP < 3) OSTORE(2);
        conv_pw<1>(X[i], H[i], V1, dil);
        if (i == OC && OSP < 4) OSTORE(3);
        wg_wait<2>();
        if (i > 0) { keepu(y); YOUT(i - 1); }
        if (nx) {
          keepu(ux); keepu(uh);
          if (lane == 0) mbar_arrive_cl(BAR(B_XFREE + 4 * wg + n), rank ^ 1);
          conv_s2(K, ux, X[n], dfl);
          wg_wait<1>();
        } else wg_wait<0>();
        keepu(V0); keepu(V1);
        conv_it<0>(K, V0, vst + vo);
        conv_it<1>(K, V1, vst + vo);
        bar_sync(1 + wg);
#pragma unroll
        for (int s = 0; s < 4; s++) ldsm4t(a[s], vld + vo + s * 512);
        if (nx) conv_s2(K, uh, H[n], dfl);
        conv_m4(y, a, d4l);
        if (i > 0 && lane < 2) mbar_arrive_cl(BAR(B_AFREE + i - 1), lane);
        if (elect) STAMP(wg, i < 2 ? 6 + i : 9 + i);
      }
      wg_wait<0>(); keepu(y);
      YOUT(3);
      if (lane == 0) mbar_arrive(BAR(B_Y));
    }
    {
      float acc[64];
#pragma unroll 1
      for (int kb = 0; kb < 16; kb++) {
        mbar_wait(BAR(B_FULL2 + kb), 0);
        if (kb == 0 && elect) { STAMP(wg, 13); GSTAMP(wg, 28); }
        const uint32_t da = s16 + ((uint32_t)(SLOT_A >> (4 * kb)) & 15) * 1024 + wg * 512 + (1 << 16);
        const uint32_t db = s16 + ((uint32_t)(SLOT_B >> (4 * kb)) & 15) * 1024 + (512 << 16);
        wg_fence();
#pragma unroll
        for (int ks = 0; ks < 4; ks++) wgmma_ss_n128<0, 1>(acc, dsc(da + ks * 2, SW128), dsc(db + ks * 128, SW128), (kb | ks) != 0);
        wg_commit();
        wg_wait<1>();
        if (kb > 0 && kb < 14 && t < 2 && (kb <= 11 || t == rank)) mbar_arrive_cl(BAR(B_CONS2 + kb - 1), t);
      }
      wg_wait<0>();
      keep(acc);
      if (elect) { STAMP(wg, 14); GSTAMP(wg, 29); }
      mbar_wait(BAR(B_CONS2 + 12), 0);
      const uint32_t stg = sb + (wg ? 5 : 2) * 16384;
      const uint32_t lrow = stg + (16 * w + 8 * ((lane >> 3) & 1) + (lane & 7)) * 128 + (((lane >> 4) ^ (lane & 7)) << 4);
#pragma unroll
      for (int cp = 0; cp < 8; cp++) {
        const float* a = &acc[8 * cp];
        stsm4((lrow ^ ((cp & 3) * 32)) + (cp >> 2) * 8192, pk2(a[0], a[1]), pk2(a[2], a[3]), pk2(a[4], a[5]), pk2(a[6], a[7]));
      }
      fence_async();
      bar_sync(1 + wg);
      if (elect) {
        const int col = 1024 + 256 * cb + 128 * rank, row = 128 * rb + 64 * wg;
        tma2d_st(&P.tmOB, stg, col, row);
        tma2d_st(&P.tmOB, stg + 8192, col + 64, row);
        asm volatile("cp.async.bulk.commit_group;\ncp.async.bulk.wait_group.read 0;" ::: "memory");
        STAMP(wg, 15); GSTAMP(wg, 31);
      }
    }
  } else {
    asm volatile("setmaxnreg.dec.sync.aligned.u32 56;");
    if (warp == 8) {
      int st = 0, ph = 1;
      const uint8_t* pfx = (const uint8_t*)P.x + (mb * 256 + hp * 16 + (lane & 15)) * 2048;
      const uint8_t* pfw = (const uint8_t*)P.w + (mb * 8 + (lane & 7)) * 6144 + (lane >> 3) * 2048 + hp * 128;
#pragma unroll 1
      for (int kb = 0; kb < 16; kb++) {
        if (kb >= 3) mbar_wait(BAR(B_EMPTY1 + st), ph);
        const uint32_t sa = sb + st * STAGE_BYTES;
        if (elect_one()) {
          mbar_expect(BAR(B_FULL1 + st), STAGE_BYTES);
          tma2d_mc(sa + rank * 16384, &P.tmX, kb * 64, mb * 256 + rank * 128, BAR(B_FULL1 + st));
          tma3d(sa + 32768, &P.tmW, hp * 64, kb * 64, 0, BAR(B_FULL1 + st));
        }
        if (PFD && kb >= 2) {
#pragma unroll 1
          for (int j = kb == 2 ? 3 : kb + PFD; j <= kb + PFD && j < 16; j++) {
            if (lane < 16) asm volatile("prefetch.global.L2 [%0];" ::"l"(pfx + j * 128));
            if (lane < 24) asm volatile("prefetch.global.L2 [%0];" ::"l"(pfw + j * (64 * 6144)));
          }
          if (kb >= QPF && kb < QPF + 8) asm volatile("prefetch.global.L2 [%0];" ::"l"((const uint8_t*)P.q + (blockIdx.x * 256 + (kb - QPF) * 32 + lane) * 128));
          if (kb >= 4)
            asm volatile("prefetch.global.L2 [%0];" ::"l"(kb < 12 ? (const uint8_t*)P.h + (blockIdx.x * 256 + (kb - 4) * 32 + lane) * 128
                                                                  : (const uint8_t*)P.wo + (blockIdx.x * 128 + (kb - 12) * 32 + lane) * 128));
        }
        if (++st == 3) { st = 0; ph ^= 1; }
      }
      if (lane == 0) STAMP(2, 1);
      const unsigned epoch = g_epoch[blockIdx.x];
#define SLOT(tab, kb) (sb + ((uint32_t)((tab) >> (4 * (kb))) & 15) * 16384)
#define LOAD_B(kb) tma3d(SLOT(SLOT_B, kb), &P.tmWo, 0, (kb) * 64, 4 * cb + 2 * rank, BAR(B_FULL2 + (kb)))
#define LOAD_A(kb) bulk_ld_mc(SLOT(SLOT_A, kb) + rank * 8192, g_o + (rb * 16 + (kb)) * 1024 + rank * 512, 8192, BAR(B_FULL2 + (kb)))
      mbar_wait(BAR(B_EMPTY1 + 1), 0);
#pragma unroll 1
      for (int kb = 0; kb < 7; kb++) {
        if (kb == 1) mbar_wait(BAR(B_EMPTY1 + 2), 0);
        if (kb == 2) mbar_wait(BAR(B_EMPTY1 + 0), 1);
        if (kb == 6) mbar_wait(BAR(BPRE), 0);
        if (elect_one()) {
          mbar_expect(BAR(B_FULL2 + kb), 16384);
          LOAD_B(kb);
          if (kb == 1) {
            mbar_expect(BAR(B_Q), 8192);
#pragma unroll 1
            for (int ci = 6; ci < 10; ci++) tma3d(sb + OFF_SPARE + 2048 * (ci - 6), &P.tmQ, 16 * cl, 64 * rank + 32 * (ci >> 3), 2 * (ci & 7), BAR(B_Q));
          }
        }
      }
      if (lane == 0) STAMP(2, 2);
      poll_ge(&g_ocnt[rb * 32], 16 * (epoch + 1));
      asm volatile("fence.proxy.async.global;" ::: "memory");
      if (lane == 0) STAMP(2, 3);
#pragma unroll 1
      for (int kb = 0; kb < 7; kb++) {
        mbar_wait(BAR(kb < 3 ? B_AFREE + kb : B_CONS2 + ((kb - 3) >> 1)), 0);
        if (elect_one()) {
          mbar_expect(BAR(B_FULL2 + kb), 16384);
          LOAD_A(kb);
        }
        if (kb == 2 && lane == 0) STAMP(2, 4);
      }
#pragma unroll 1
      for (int kb = 7; kb < 16; kb++) {
        mbar_wait(BAR(B_CONS2 + kb - 5), 0);
        if (elect_one()) { mbar_expect(BAR(B_FULL2 + kb), 32768); LOAD_A(kb); LOAD_B(kb); }
      }
      if (lane == 0) { g_epoch[blockIdx.x] = epoch + 1; STAMP(2, 5); }
    } else {
      const uint32_t clk0 = clock();
      const int hw = warp - 9, g = lane >> 2, q = lane & 3;
      const unsigned epoch = g_epoch[blockIdx.x];
      const uint32_t tag = ~epoch & 1;
      const uint32_t stg = sb + OFF_STG + hw * STG_STRIDE, sbar = BAR(B_STG + 2 * hw);
      int ph = 0;
      {
        uint32_t tap[2][4];
#pragma unroll
        for (int cg = 0; cg < 2; cg++) {
          const uint2 u = __ldg((const uint2*)(P.shift_k + (16 * cl + 8 * cg + g) * 4));
          tap[cg][0] = __byte_perm(u.x, 0, 0x1010); tap[cg][1] = __byte_perm(u.x, 0, 0x3232);
          tap[cg][2] = __byte_perm(u.y, 0, 0x1010); tap[cg][3] = __byte_perm(u.y, 0, 0x3232);
        }
        if (hw == 0 && lane < 8) *(float*)(smem + OFF_D + 4 * lane) = __bfloat162float(P.D[blockIdx.x * 8 + lane]);
        if (hw == 1) asm volatile("prefetch.global.L2 [%0];" ::"l"(c_thr + (lane + 32 * (blockIdx.x & 1)) * 32));
        if (hw == 0 && elect_one()) {
          *(volatile unsigned*)(smem + OFF_EPOCH) = epoch;
          mbar_expect(BAR(B_XRAW), 32768);
          mbar_expect(BAR(B_Y), 32768 + 64);
        }
        if (lane == 0) STAMP(3, hw);
        const uint32_t xo = sb + OFF_XT + g * XT_STRIDE + rank * 2048 + q * 4;
        const int krow = 8 + (lane & 7) - (lane >> 3);
        const uint32_t ka = stg + krow * 32 + ((krow & 4) << 2), va = stg + 2304 + lane * 32 + ((lane & 4) << 2);
        int b = 0;
#pragma unroll 1
        for (int ci = hw - 3; ci < 16; ci += 3) {
          const uint32_t bo = b ? OFF_F2F - OFF_STG : 0, bn = b ? 0 : OFF_F2F - OFF_STG;
          if (ci + 3 < 16) {
            while ((uint32_t)clock() - clk0 < HSTART + (ci + 3) * PACE) __nanosleep(64);
            if (elect_one()) {
              mbar_expect(sbar + 8 * (b ^ 1), 2304 + 2048);
              tma2d(stg + bn, &P.tmK, 16 * cl, 1024 * rank + 64 * (ci + 3) - 8, sbar + 8 * (b ^ 1));
              tma2d(stg + bn + 2304, &P.tmV, 16 * cl, 1024 * rank + 64 * (ci + 3), sbar + 8 * (b ^ 1));
            }
          }
          if (ci >= 0) {
            mbar_wait(sbar + 8 * b, (ph >> b) & 1);
            ph ^= 1 << b;
#pragma unroll 1
            for (int grp = 0; grp < 2; grp++) {
#pragma unroll
              for (int cg = 0; cg < 2; cg++) {
                const uint32_t dst = mapa(xo + (ci >> 3) * 1024 + ((ci & 7) * 4 + 2 * grp) * 16, cg), xbar = mapa(BAR(B_XRAW), cg);
                uint32_t vv[4], kk[4][4];
                ldsm4t(vv, (va ^ (cg * 16)) + bo + grp * 1024);
#pragma unroll
                for (int rg = 0; rg < 4; rg++) ldsm4t(kk[rg], (ka ^ (cg * 16)) + bo + grp * 1024 + rg * 256);
#pragma unroll
                for (int rg = 0; rg < 4; rg++)
                  vv[rg] = hmul(hadd(hadd(hadd(hmul(kk[rg][3], tap[cg][3]), hmul(kk[rg][2], tap[cg][2])), hmul(kk[rg][1], tap[cg][1])), hmul(kk[rg][0], tap[cg][0])), vv[rg]);
#pragma unroll
                for (int rg = 0; rg < 4; rg++) st_async(dst + (rg & 1) * 512 + (rg >> 1) * 16, vv[rg], xbar);
              }
            }
          }
          b ^= 1;
        }
      }
      if (lane == 0) STAMP(3, 3 + hw);
      asm volatile("bar.sync 4, 96;" ::: "memory");
      if (hw == 0 && elect_one()) { mbar_expect(BAR(B_XT), 10240); bulk_ld(sb + OFF_F2F, c_img, 10240, BAR(B_XT)); }
      mbar_wait(BAR(B_XRAW), 0);
#pragma unroll 1
      for (int c = hw; c < 8; c += 3) {
        uint4* p = (uint4*)(smem + OFF_XT + c * XT_STRIDE) + lane;
        uint32_t v[32];
#pragma unroll
        for (int i = 0; i < 8; i++) { const uint4 u = p[i * 32]; v[4 * i] = u.x; v[4 * i + 1] = u.y; v[4 * i + 2] = u.z; v[4 * i + 3] = u.w; }
        const int e = normalise(v, 0.f);
#pragma unroll
        for (int i = 0; i < 8; i++) p[i * 32] = make_uint4(v[4 * i], v[4 * i + 1], v[4 * i + 2], v[4 * i + 3]);
        if (lane == 0) smem[OFF_EX + c] = e;
        if (c < 6 && elect_one()) {
          if (c < 3) mbar_expect(sbar, 4096);
          tma3d(sb + OFF_STG + 2048 * c, &P.tmQ, 16 * cl, 64 * rank, 2 * c, sbar);
        }
      }
      fence_async();
      __syncwarp();
      if (lane == 0) { mbar_arrive(BAR(B_XT)); STAMP(3, 13 + hw); }
      mbar_wait(BAR(B_PKFREE), 0);
      if (hw == 0 && lane == 0) STAMP(3, 19);
      if (PD1) __nanosleep(PD1);
      {
        const int pi = hw < 2 ? 64 * mb + 32 * hw + lane : 512 + 2 * mb + (lane & 1);
        uint4 f[8];
        int n = 0;
        uint32_t bad;
        do {
#pragma unroll
          for (int p = 0; p < 8; p++) f[p] = ld_rlx4(&g_part[hp][p][4 * pi]);
          bad = stale8(f, tag);
          if (++n > SPIN_LIMIT) __trap();
        } while (__any_sync(~0u, bad & 1));
        float s0 = 0.f, s1 = 0.f, s2 = 0.f, s3 = 0.f;
#pragma unroll
        for (int p = 0; p < 8; p++) { s0 += __uint_as_float(f[p].x); s1 += __uint_as_float(f[p].y); s2 += __uint_as_float(f[p].z); s3 += __uint_as_float(f[p].w); }
        if (hw < 2 || lane < 2) st_tag4(&g_kv[hp][4 * pi], s0, s1, s2, s3, tag);
      }
      if (lane == 0 && hw == 0) STAMP(3, 8);
      if (hw == 2) {
        mbar_wait(BAR(B_ODONE), 0);
        if (lane < 2) {
          asm volatile("red.release.gpu.global.add.u32 [%0], 1;" ::"l"(&g_ocnt[(2 * mb + lane) * 32]) : "memory");
        }
        if (lane == 0) STAMP(3, 7);
        __syncwarp();
      } else {
        if (PD2) __nanosleep(PD2);
        const int t = hw * 32 + lane;
        uint4 f[8];
        uint4 zp;
        uint32_t bad;
        int n = 0;
        do {
          zp = ld_rlx4(&g_kv[hp][2048 + (t & 48) + 2 * (lane & 6)]);
#pragma unroll
          for (int p = 0; p < 8; p++) f[p] = ld_rlx4(&g_kv[hp][4 * ((p & 3) * 128 + (p >> 2) * 64 + t)]);
          bad = stale8(f, tag) | (zp.x ^ tag);
          if (++n > SPIN_LIMIT) __trap();
        } while (__any_sync(~0u, bad & 1));
#define PK2U(a, b) pk2(__uint_as_float(a), __uint_as_float(b))
#pragma unroll
        for (int hh = 0; hh < 2; hh++) {
          const uint4* ff = &f[4 * hh];
          uint8_t* dst = smem + OFF_KVB + hh * 2560 + q * 512 + (16 * hw + g) * 16;
          *(uint4*)dst = make_uint4(PK2U(ff[0].x, ff[0].y), PK2U(ff[1].x, ff[1].y), PK2U(ff[2].x, ff[2].y), PK2U(ff[3].x, ff[3].y));
          *(uint4*)(dst + 128) = make_uint4(PK2U(ff[0].z, ff[0].w), PK2U(ff[1].z, ff[1].w), PK2U(ff[2].z, ff[2].w), PK2U(ff[3].z, ff[3].w));
        }
        const uint32_t zf = (lane & 1) ? ((lane & 8) ? zp.w : zp.z) : ((lane & 8) ? zp.y : zp.x);
        const uint32_t zz = PK2U(zf, zf);
        *(uint4*)(smem + OFF_KVB + hw * 2560 + 2048 + lane * 16) = make_uint4(zz, zz, zz, zz);
        fence_async();
        __syncwarp();
        if (lane == 0) { mbar_arrive(BAR(B_KV)); if (hw == 0) STAMP(3, 9); }
      }
#define QBUF(ci) (sb + 2048 * (ci) + ((ci) < 6 ? OFF_STG : (ci) < 10 ? OFF_SPARE - 6 * 2048 : OFF_F2F - 10 * 2048))
      mbar_wait(BAR(B_Y), 0);
      if (elect_one()) {
        mbar_expect(sbar + 8, 4096);
#pragma unroll 1
        for (int ci = hw ? hw + 9 : 12; ci < 16; ci += 3) tma3d(QBUF(ci), &P.tmQ, 16 * cl, 64 * rank + 32, 2 * (ci & 7), sbar + 8);
      }
      mbar_wait(BAR(B_Q), 0);
      {
        const float2 sc0 = *(const float2*)(smem + OFF_SCALE + 8 * q), sc1 = *(const float2*)(smem + OFF_SCALE + 32 + 8 * q);
        const uint32_t yl = sb + OFF_XT + (lane & 7) * XT_STRIDE + (lane >> 3) * 16;
#pragma unroll 1
        for (int ci = hw; ci < 16; ci += 3) {
          const uint32_t qb = QBUF(ci);
          const int b = ci >= 10;
          mbar_wait(sbar + 8 * b, (ph >> b) & 1);
#pragma unroll 1
          for (int nl = 0; nl < 2; nl++) {
            uint32_t yy[2][4], qq[2][4];
            const uint32_t qa = qb + lane * 32 + ((lane & 4) << 2) + nl * 1024;
#pragma unroll
            for (int cg = 0; cg < 2; cg++) { ldsm4t(yy[cg], yl + cg * 2048 + (2 * ci + nl) * 64); ldsm4(qq[cg], qa ^ (cg * 16)); }
#pragma unroll
            for (int cg = 0; cg < 2; cg++) {
              const float2 sc = cg ? sc1 : sc0;
#pragma unroll
              for (int m = 0; m < 4; m++) {
                const float2 f = __half22float2(*(const __half2*)&yy[cg][m]);
                qq[cg][m] = hmul(qq[cg][m], pk2(f.x * sc.x, f.y * sc.y));
              }
              stsm4(qa ^ (cg * 16), qq[cg][0], qq[cg][1], qq[cg][2], qq[cg][3]);
            }
          }
          fence_async();
          __syncwarp();
          if (elect_one()) tma3d_st(&P.tmOA, qb, 16 * cl, 64 * rank + 32 * (ci >> 3), 2 * (ci & 7));
        }
        asm volatile("cp.async.bulk.commit_group;\ncp.async.bulk.wait_group.read 0;" ::: "memory");
      }
      if (lane == 0) STAMP(3, 10 + hw);
    }
  }
}

typedef CUresult (*EncodeFn)(CUtensorMap*, CUtensorMapDataType, cuuint32_t, void*, const cuuint64_t*, const cuuint64_t*,
                             const cuuint32_t*, const cuuint32_t*, CUtensorMapInterleave, CUtensorMapSwizzle,
                             CUtensorMapL2promotion, CUtensorMapFloatOOBfill);

static void enc(EncodeFn fn, CUtensorMap* m, const void* p, int rank, const cuuint64_t* dims, const cuuint64_t* strides,
                const cuuint32_t* box, CUtensorMapSwizzle swz, CUtensorMapL2promotion promo) {
  cuuint32_t es[3] = {1, 1, 1};
  fn(m, CU_TENSOR_MAP_DATA_TYPE_BFLOAT16, rank, (void*)p, dims, strides, box, es, CU_TENSOR_MAP_INTERLEAVE_NONE, swz, promo,
     CU_TENSOR_MAP_FLOAT_OOB_FILL_NONE);
}

extern "C" void kernel_launch(void* const* d_in, const int* in_sizes, int n_in, void* d_out, int out_size) {
  void* fp = nullptr;
  cudaDriverEntryPointQueryResult qr;
  cudaGetDriverEntryPoint("cuTensorMapEncodeTiled", &fp, cudaEnableDefault, &qr);
  EncodeFn fn = (EncodeFn)fp;
  Params P;
  P.shift_k = (const __nv_bfloat16*)d_in[3]; P.h = (const __nv_bfloat16*)d_in[4]; P.D = (const __nv_bfloat16*)d_in[5];
  P.q = (const __nv_bfloat16*)d_in[0];
  P.x = (const __nv_bfloat16*)d_in[6]; P.w = (const __nv_bfloat16*)d_in[7]; P.wo = (const __nv_bfloat16*)d_in[8];
  const CUtensorMapSwizzle S128 = CU_TENSOR_MAP_SWIZZLE_128B, S32 = CU_TENSOR_MAP_SWIZZLE_32B;
  const CUtensorMapL2promotion P0 = CU_TENSOR_MAP_L2_PROMOTION_NONE, P128 = CU_TENSOR_MAP_L2_PROMOTION_L2_128B;
  { cuuint64_t d[2] = {1024, 2048}, s[1] = {2048}; cuuint32_t b[2] = {64, 128}; enc(fn, &P.tmX, d_in[6], 2, d, s, b, S128, P128); }
  { cuuint64_t d[3] = {1024, 1024, 3}, s[2] = {6144, 2048}; cuuint32_t b[3] = {64, 64, 3}; enc(fn, &P.tmW, d_in[7], 3, d, s, b, S128, P128); }
  { cuuint64_t d[3] = {64, 1024, 16}, s[2] = {2048, 128}; cuuint32_t b[3] = {64, 64, 2}; enc(fn, &P.tmWo, d_in[8], 3, d, s, b, S128, P128); }
  { cuuint64_t d[2] = {1024, 2048}, s[1] = {2048}; cuuint32_t b[2] = {16, 72}; enc(fn, &P.tmK, d_in[1], 2, d, s, b, S32, PKV); }
  { cuuint64_t d[2] = {1024, 2048}, s[1] = {2048}; cuuint32_t b[2] = {16, 64}; enc(fn, &P.tmV, d_in[2], 2, d, s, b, S32, PKV); }
  { cuuint64_t d[3] = {1024, 128, 16}, s[2] = {32768, 2048}; cuuint32_t b[3] = {16, 32, 2}; enc(fn, &P.tmQ, d_in[0], 3, d, s, b, S32, PKV); }
  { cuuint64_t d[3] = {1024, 128, 16}, s[2] = {65536, 4096}; cuuint32_t b[3] = {16, 32, 2}; enc(fn, &P.tmOA, d_out, 3, d, s, b, S32, P0); }
  { cuuint64_t d[2] = {2048, 2048}, s[1] = {4096}; cuuint32_t b[2] = {64, 64}; enc(fn, &P.tmOB, d_out, 2, d, s, b, S128, P0); }
  cudaFuncSetAttribute(fused_kernel, cudaFuncAttributeMaxDynamicSharedMemorySize, SMEM_TOTAL);
  fused_kernel<<<128, 384, SMEM_TOTAL>>>(P);
}
```

```cpp
#include <cuda_runtime.h>
#include <cuda_bf16.h>
#include <cuda_fp16.h>
#include <cuda.h>
#include <stdint.h>

template<int TA, int TB, int SA=1> __device__ __forceinline__ void wgmma_ss_n192(float (&d)[96], uint64_t da, uint64_t db, int scale_d) {
  asm volatile("{\n.reg .pred p;\nsetp.ne.b32 p, %98, 0;\n"
    "wgmma.mma_async.sync.aligned.m64n192k16.f32.bf16.bf16 {%0, %1, %2, %3, %4, %5, %6, %7, %8, %9, %10, %11, %12, %13, %14, %15, %16, %17, %18, %19, %20, %21, %22, %23, %24, %25, %26, %27, %28, %29, %30, %31, %32, %33, %34, %35, %36, %37, %38, %39, %40, %41, %42, %43, %44, %45, %46, %47, %48, %49, %50, %51, %52, %53, %54, %55, %56, %57, %58, %59, %60, %61, %62, %63, %64, %65, %66, %67, %68, %69, %70, %71, %72, %73, %74, %75, %76, %77, %78, %79, %80, %81, %82, %83, %84, %85, %86, %87, %88, %89, %90, %91, %92, %93, %94, %95}, %96, %97, p, %101, 1, %99, %100;\n}\n"
    : "+f"(d[0]), "+f"(d[1]), "+f"(d[2]), "+f"(d[3]), "+f"(d[4]), "+f"(d[5]), "+f"(d[6]), "+f"(d[7]), "+f"(d[8]), "+f"(d[9]), "+f"(d[10]), "+f"(d[11]), "+f"(d[12]), "+f"(d[13]), "+f"(d[14]), "+f"(d[15]), "+f"(d[16]), "+f"(d[17]), "+f"(d[18]), "+f"(d[19]), "+f"(d[20]), "+f"(d[21]), "+f"(d[22]), "+f"(d[23]), "+f"(d[24]), "+f"(d[25]), "+f"(d[26]), "+f"(d[27]), "+f"(d[28]), "+f"(d[29]), "+f"(d[30]), "+f"(d[31]), "+f"(d[32]), "+f"(d[33]), "+f"(d[34]), "+f"(d[35]), "+f"(d[36]), "+f"(d[37]), "+f"(d[38]), "+f"(d[39]), "+f"(d[40]), "+f"(d[41]), "+f"(d[42]), "+f"(d[43]), "+f"(d[44]), "+f"(d[45]), "+f"(d[46]), "+f"(d[47]), "+f"(d[48]), "+f"(d[49]), "+f"(d[50]), "+f"(d[51]), "+f"(d[52]), "+f"(d[53]), "+f"(d[54]), "+f"(d[55]), "+f"(d[56]), "+f"(d[57]), "+f"(d[58]), "+f"(d[59]), "+f"(d[60]), "+f"(d[61]), "+f"(d[62]), "+f"(d[63]), "+f"(d[64]), "+f"(d[65]), "+f"(d[66]), "+f"(d[67]), "+f"(d[68]), "+f"(d[69]), "+f"(d[70]), "+f"(d[71]), "+f"(d[72]), "+f"(d[73]), "+f"(d[74]), "+f"(d[75]), "+f"(d[76]), "+f"(d[77]), "+f"(d[78]), "+f"(d[79]), "+f"(d[80]), "+f"(d[81]), "+f"(d[82]), "+f"(d[83]), "+f"(d[84]), "+f"(d[85]), "+f"(d[86]), "+f"(d[87]), "+f"(d[88]), "+f"(d[89]), "+f"(d[90]), "+f"(d[91]), "+f"(d[92]), "+f"(d[93]), "+f"(d[94]), "+f"(d[95])
    : "l"(da), "l"(db), "r"(scale_d), "n"(TA), "n"(TB), "n"(SA));
}
template<int TA, int TB, int SA=1> __device__ __forceinline__ void wgmma_ss_n128(float (&d)[64], uint64_t da, uint64_t db, int scale_d) {
  asm volatile("{\n.reg .pred p;\nsetp.ne.b32 p, %66, 0;\n"
    "wgmma.mma_async.sync.aligned.m64n128k16.f32.bf16.bf16 {%0, %1, %2, %3, %4, %5, %6, %7, %8, %9, %10, %11, %12, %13, %14, %15, %16, %17, %18, %19, %20, %21, %22, %23, %24, %25, %26, %27, %28, %29, %30, %31, %32, %33, %34, %35, %36, %37, %38, %39, %40, %41, %42, %43, %44, %45, %46, %47, %48, %49, %50, %51, %52, %53, %54, %55, %56, %57, %58, %59, %60, %61, %62, %63}, %64, %65, p, %69, 1, %67, %68;\n}\n"
    : "+f"(d[0]), "+f"(d[1]), "+f"(d[2]), "+f"(d[3]), "+f"(d[4]), "+f"(d[5]), "+f"(d[6]), "+f"(d[7]), "+f"(d[8]), "+f"(d[9]), "+f"(d[10]), "+f"(d[11]), "+f"(d[12]), "+f"(d[13]), "+f"(d[14]), "+f"(d[15]), "+f"(d[16]), "+f"(d[17]), "+f"(d[18]), "+f"(d[19]), "+f"(d[20]), "+f"(d[21]), "+f"(d[22]), "+f"(d[23]), "+f"(d[24]), "+f"(d[25]), "+f"(d[26]), "+f"(d[27]), "+f"(d[28]), "+f"(d[29]), "+f"(d[30]), "+f"(d[31]), "+f"(d[32]), "+f"(d[33]), "+f"(d[34]), "+f"(d[35]), "+f"(d[36]), "+f"(d[37]), "+f"(d[38]), "+f"(d[39]), "+f"(d[40]), "+f"(d[41]), "+f"(d[42]), "+f"(d[43]), "+f"(d[44]), "+f"(d[45]), "+f"(d[46]), "+f"(d[47]), "+f"(d[48]), "+f"(d[49]), "+f"(d[50]), "+f"(d[51]), "+f"(d[52]), "+f"(d[53]), "+f"(d[54]), "+f"(d[55]), "+f"(d[56]), "+f"(d[57]), "+f"(d[58]), "+f"(d[59]), "+f"(d[60]), "+f"(d[61]), "+f"(d[62]), "+f"(d[63])
    : "l"(da), "l"(db), "r"(scale_d), "n"(TA), "n"(TB), "n"(SA));
}
template<int TA, int TB, int SA=1> __device__ __forceinline__ void wgmma_ss_n72(float (&d)[36], uint64_t da, uint64_t db, int scale_d) {
  asm volatile("{\n.reg .pred p;\nsetp.ne.b32 p, %38, 0;\n"
    "wgmma.mma_async.sync.aligned.m64n72k16.f32.bf16.bf16 {%0, %1, %2, %3, %4, %5, %6, %7, %8, %9, %10, %11, %12, %13, %14, %15, %16, %17, %18, %19, %20, %21, %22, %23, %24, %25, %26, %27, %28, %29, %30, %31, %32, %33, %34, %35}, %36, %37, p, %41, 1, %39, %40;\n}\n"
    : "+f"(d[0]), "+f"(d[1]), "+f"(d[2]), "+f"(d[3]), "+f"(d[4]), "+f"(d[5]), "+f"(d[6]), "+f"(d[7]), "+f"(d[8]), "+f"(d[9]), "+f"(d[10]), "+f"(d[11]), "+f"(d[12]), "+f"(d[13]), "+f"(d[14]), "+f"(d[15]), "+f"(d[16]), "+f"(d[17]), "+f"(d[18]), "+f"(d[19]), "+f"(d[20]), "+f"(d[21]), "+f"(d[22]), "+f"(d[23]), "+f"(d[24]), "+f"(d[25]), "+f"(d[26]), "+f"(d[27]), "+f"(d[28]), "+f"(d[29]), "+f"(d[30]), "+f"(d[31]), "+f"(d[32]), "+f"(d[33]), "+f"(d[34]), "+f"(d[35])
    : "l"(da), "l"(db), "r"(scale_d), "n"(TA), "n"(TB), "n"(SA));
}
template<int TB, int SA=1> __device__ __forceinline__ void wgmma_rs_n40(float (&d)[20], uint32_t a0, uint32_t a1, uint32_t a2, uint32_t a3, uint64_t db, int scale_d) {
  asm volatile("{\n.reg .pred p;\nsetp.ne.b32 p, %25, 0;\n"
    "wgmma.mma_async.sync.aligned.m64n40k16.f32.bf16.bf16 {%0, %1, %2, %3, %4, %5, %6, %7, %8, %9, %10, %11, %12, %13, %14, %15, %16, %17, %18, %19}, {%20, %21, %22, %23}, %24, p, %27, 1, %26;\n}\n"
    : "+f"(d[0]), "+f"(d[1]), "+f"(d[2]), "+f"(d[3]), "+f"(d[4]), "+f"(d[5]), "+f"(d[6]), "+f"(d[7]), "+f"(d[8]), "+f"(d[9]), "+f"(d[10]), "+f"(d[11]), "+f"(d[12]), "+f"(d[13]), "+f"(d[14]), "+f"(d[15]), "+f"(d[16]), "+f"(d[17]), "+f"(d[18]), "+f"(d[19])
    : "r"(a0), "r"(a1), "r"(a2), "r"(a3), "l"(db), "r"(scale_d), "n"(TB), "n"(SA));
}
template<int TB> __device__ __forceinline__ void wgmma_hrs_n64(uint32_t (&d)[16], uint32_t a0, uint32_t a1, uint32_t a2, uint32_t a3, uint64_t db, int scale_d) {
  asm volatile("{\n.reg .pred p;\nsetp.ne.b32 p, %21, 0;\n"
    "wgmma.mma_async.sync.aligned.m64n64k16.f16.f16.f16 {%0, %1, %2, %3, %4, %5, %6, %7, %8, %9, %10, %11, %12, %13, %14, %15}, {%16, %17, %18, %19}, %20, p, 1, 1, %22;\n}\n"
    : "+r"(d[0]), "+r"(d[1]), "+r"(d[2]), "+r"(d[3]), "+r"(d[4]), "+r"(d[5]), "+r"(d[6]), "+r"(d[7]), "+r"(d[8]), "+r"(d[9]), "+r"(d[10]), "+r"(d[11]), "+r"(d[12]), "+r"(d[13]), "+r"(d[14]), "+r"(d[15])
    : "r"(a0), "r"(a1), "r"(a2), "r"(a3), "l"(db), "r"(scale_d), "n"(TB));
}
template<int TB> __device__ __forceinline__ void wgmma_hrs_n32(uint32_t (&d)[8], uint32_t a0, uint32_t a1, uint32_t a2, uint32_t a3, uint64_t db, int scale_d) {
  asm volatile("{\n.reg .pred p;\nsetp.ne.b32 p, %13, 0;\n"
    "wgmma.mma_async.sync.aligned.m64n32k16.f16.f16.f16 {%0, %1, %2, %3, %4, %5, %6, %7}, {%8, %9, %10, %11}, %12, p, 1, 1, %14;\n}\n"
    : "+r"(d[0]), "+r"(d[1]), "+r"(d[2]), "+r"(d[3]), "+r"(d[4]), "+r"(d[5]), "+r"(d[6]), "+r"(d[7])
    : "r"(a0), "r"(a1), "r"(a2), "r"(a3), "l"(db), "r"(scale_d), "n"(TB));
}

__device__ __align__(128) const uint32_t c_thr[1536] = {
  0x33fb33ff,0xa49c9de4,0x33273352,0xaf2cae76,0x33e233f1,0xa96ca7bd,0x32c432f7,0xb045afdd,0x33b733cf,0xac3eaaf7,0x3250328c,0xb0eab099,
  0x3378339a,0xadbcacff,0x31cd3211,0xb182b137,0x33d033fb,0xaadea46a,0x299e2d17,0xb3e0b396,0x32fb337a,0xafd2adb1,0xa78b1f76,0xb3f2b3ff,
  0x318b3254,0xb1c5b0e5,0xae6bac32,0xb354b3b8,0x2f4230a3,0xb321b285,0xb133b040,0xb215b2c7,0x337c33f2,0xada5a759,0xb179afc8,0xb1d6b2fe,
  0x31463293,0xb204b08e,0xb394b2ba,0xad23b055,0x2b402f4e,0xb3cbb31e,0xb3e4b3f9,0x293ba533,0xac269c52,0xb3bab400,0xb258b357,0x30e02e5f,
  0x330133e5,0xafbda922,0xb3f3b3c9,0x2727ab59,0x2deb314a,0xb36fb200,0xb194b32f,0x31bc2f0a,0xacdb2084,0xb39fb3ff,0xa565aea4,0x33f93347,
  0xb2b6b0db,0xb05ab25c,0x30892c1a,0x329733bc,0x326033d4,0xb0d6aa94,0xb00ab29b,0x32e83084,0x20e82f64,0xb3feb318,0x2d8da597,0x338133f8,
  0xb1fcae48,0xb14fb35c,0x339031b8,0x2d3a3199,0xb3e6b3ae,0x2909ac7b,0x32d133f4,0xb030a6f5,0x319d33bf,0xb1b3ac02,0x2e3ca874,0x335e33ec,
  0xacc32b89,0xb3a3b3c6,0x33f83276,0x25c930b7,0xb3dcb1f8,0xaa01b154,0x30653335,0xb2b0aef4,0xb107b383,0x32392d81,0xafa6214d,0xb307b3fe,
  0x30bc33a5,0xb273acb7,0x33c5311b,0x2ba23229,0xb0cc94b6,0xb267b400,0x30153360,0xb2e1ae31,0xb385b3ab,0x2d76ac93,0xb166a691,0xb1e7b3f5,
  0x22deb06a,0x33fd32ac,0xb337b3da,0x2ee8aa19,0x2f853387,0xb310ad6a,0x322d33fe,0xb1162216,0xb2a9abd3,0xb06fb3c2,0xb07428a6,0xb2a5b3ea,
  0xb111b3e9,0x323128be,0xb30db3c3,0x2f90abba,0x31aa227a,0x31a633fd,0x2e25ad5e,0x33633389,0x2d6a3365,0xb387ae1a,0xa21631aa,0xb3feb1a6,
  0xb3c2af85,0xabd3b310,0xb3eab22d,0x28a6b116,0xa8beb2a9,0x33e9306f,0x2bbab074,0x33c332a5,0x33fd3111,0x227a3231,0x3389330d,0xad5e2f90,
  0x2a63333f,0xb3d7aec6,0xb2a2a1b1,0xb07ab3fe,0xb3f7b158,0x25fbb1f4,0xacb7b38b,0x33a52d52,0x2e0eb025,0x336832d8,0x340030bc,0x14b63273,
  0x323533c0,0xb10c2beb,0xac9330cc,0xb3abb267,0x23433316,0xb3fdaf6f,0xb38eb225,0x2d46b11f,0xb342b29e,0x2ebbb07f,0x31e3aa7c,0x316b33d6,
  0x3264a6c3,0x30d133f5,0x2c0233ac,0xb3bfac87,0x28f0336a,0xb3e7ae02,0xb3c6b19d,0x2b89b1b3,0xa59732e8,0xb3f8b00a,0xaccfb3ed,0x33a1285b,
  0xb1b8b381,0x3199ad8d,0x336c31df,0xadf73170,0x33f42d3a,0x26f53390,0xb30423a7,0xafb2b3fc,0xb05f3030,0xb2b3b2d1,0x29e8b27a,0x33dd30b2,
  0xab5932b6,0xb3c9b05a,0x30adb089,0x327e3297,0xaf0ab3f3,0x332fa727,0x240633b0,0xb3fcac6f,0x33473194,0xaea431bc,0xb174b359,0x31daae54,
  0xb3bca565,0xac1ab3f9,0x33ee2f59,0xa842331b,0xaddf3281,0xb371b0a8,0x34002b40,0x1c5233cb,0xa759b3ef,0x33f22829,0xb2fe2c26,0xafc8b3ba,
  0x308e337c,0xb2932da5,0x3055b179,0x32ba31d6,0xb31eb146,0x2f4eb204,0xa5333394,0xb3f9ad23,0xaff33249,0xb2f1b0f3,0x30e532fb,0xb2542fd2,
  0x2b28b373,0x33cc2dd4,0xb285b18b,0x30a3b1c5,0x246a33fa,0xb3fba500,0x33962f42,0xad173321,0xadb1b3d0,0x337aaade,0xb3ffa99e,0x1f76b3e0,
  0xb0ee320d,0xb24db13c,0xac4b3398,0xb3b5ad0b,0x304ab289,0x32c1309e,0x2985b3ce,0x33e12b0f,0xaf3732f4,0xb324afe8,0xa4ce33f0,0xb3faa7ef,
  0x2dc8b34f,0x33762e82,0x9de4b3ff,0x33ff1ead,0xb1c931cd,0xb186b182,0xb3762e82,0xadc8b34f,0x324db13c,0x30ee320d,0x33b5ad0b,0x2c4b3398,
  0xb2c1309e,0xb04ab289,0xb3e12b0f,0xa985b3ce,0x3324afe8,0x2f3732f4,0x33faa7ef,0x24ce33f0,0xb285318b,0xb0a3b1c5,0xb2c7ae6b,0x3040b354,
  0x3396af42,0x2d173321,0x31413133,0xb2093215,0xb3ff299e,0x9f76b3e0,0xae8db2bd,0x334cb050,0x33b8278b,0xac3233f2,0x281033b3,0xb3ef2c57,
  0xb31e3146,0xaf4eb204,0xa533b394,0x33f9ad23,0x3400ab40,0x9c5233cb,0xae5f33e4,0xb357a93b,0xb2feac26,0x2fc8b3ba,0x3245b258,0x30f830e0,
  0x30553179,0xb2ba31d6,0xb3df2e99,0xa9b6b34a,0xb39230fd,0xad2fb241,0x3200b301,0x314a2fbd,0x337f1b11,0xad993400,0xb3ff2deb,0xa084b36f,
  0xb005b129,0x32ebb21d,0x325c2cdb,0xb0db339f,0xa92233de,0xb3e529cf,0xab59b2b6,0x33c9b05a,0xb3dd30b2,0xa9e8b27a,0x33d4ab71,0xaa9433c8,
  0x32212c0e,0xb12433bd,0xaf64b0d6,0x3318b260,0x197fb345,0x3400aeaf,0xae4833fe,0xb35c20e8,0xb23d3332,0xb102aeff,0x33aeb14f,0x2c7b31fc,
  0xb3fe3065,0xa14db2b0,0x2ebb307f,0xb342329e,0x300f2fa6,0xb2e53307,0x30d1b3f5,0x326426c3,0x302ab400,0x32d517db,0xb3e72e02,0x28f0b36a,
  0xb3fd2f6f,0x2343b316,0x2d46311f,0xb38e3225,0xb3f53015,0x2691b2e1,0xaf9b33eb,0xb30a288d,0x2a193166,0xb3da31e7,0x33d7aec6,0xaa63333f,
  0x3313b337,0x2f7a2ee8,0xa5fbb1f4,0x33f7b158,0xb1a1a8d7,0x31afb3e8,0xb36832d8,0xae0eb025,0xb3c22f85,0x2bd3b310,0xb3ea322d,0xa8a6b116,
  0xa8be32a9,0xb3e9306f,0x2bba3074,0xb3c332a5,0x33fdb111,0xa27a3231,0x3389b30d,0x2d5e2f90,0xa216b1aa,0x33feb1a6,0xaed2ae25,0x333db363,
  0xb3652edd,0x2e1ab33a,0xb1aa227a,0x31a6b3fd,0xaf853387,0xb3102d6a,0xb22d33fe,0xb116a216,0x32a9abd3,0xb06f33c2,0x307428a6,0xb2a533ea,
  0x3111b3e9,0x3231a8be,0x330db3c3,0x2f902bba,0xb2e12e31,0x3015b360,0x288db1a1,0x33ebb1af,0xb1e733f5,0xb1662691,0xb33f2f9b,0x2ec6b30a,
  0x2ee82a19,0xb33733da,0xb15833d7,0xb1f42a63,0x33e8b313,0x28d72f7a,0x302525fb,0xb2d833f7,0xb2392d81,0x3107b383,0x3307b3fe,0x2fa6214d,
  0xb35e33ec,0xae3ca874,0x97dbb00f,0x3400b2e5,0xa5c930b7,0xb3f83276,0xb316302a,0x2f6fb2d5,0x32b0aef4,0xb0653335,0xb29e33fd,0xb07f2343,
  0xb1702ccf,0x31dfb3a1,0x3345b124,0xaeaf3221,0xb3fc336c,0xa3a7adf7,0x3332b400,0x2eff997f,0xb0b23304,0xb27a2fb2,0x2b71b102,0x33c8b23d,
  0x2c0e29e8,0xb3bd33dd,0xb0d62a94,0x3260b3d4,0xb0892c1a,0x3297b3bc,0x2aad2842,0xb3d333ee,0xb3b0327e,0x2c6fb0ad,0x3241b035,0xb0fd32ce,
  0xb35933fc,0xae542406,0x3400b392,0x1b112d2f,0xaf5931da,0xb31b3174,0x321db37f,0x3129ad99,0xaf152ac6,0x332cb3d2,0xb1463293,0xb204308e,
  0xb281312e,0x30a8b219,0xab402f4e,0xb3cb331e,0xb3ef3371,0x2829addf,0x2c269c52,0xb3ba3400,0xb37c33f2,0xada52759,0x3179afc8,0xb1d632fe,
  0xacf32953,0x339cb3e3,0xb3fa33cc,0x2500ab28,0xb0942f21,0x3290b32a,0xb3d033fb,0xaade246a,0xb249317d,0x30f3b1d2,0xb2fb337a,0xafd22db1,
  0xb37332f1,0x2dd4aff3,0xb18b3254,0xb1c530e5,0xa96c27bd,0x33e2b3f1,0xb0452fdd,0x32c4b2f7,0xac3e2af7,0x33b7b3cf,0xb0ea3099,0x3250b28c,
  0xadbc2cff,0x3378b39a,0xb1823137,0x31cdb211,0xaf2c2e76,0x3327b352,0xb20d31c9,0x313cb186,0x313c3186,0xb20db1c9,0x2d0b2dc8,0xb398b376,
  0x309e30ee,0xb289b24d,0x2b0f2c4b,0xb3ceb3b5,0x2fe8304a,0xb2f4b2c1,0x27ef2985,0xb3f0b3e1,0x2e822f37,0xb34fb324,0x1ead24ce,0xb3ffb3fa,
  0xb2bdb209,0xb050b141,0xb290b32a,0x30942f21,0xb3b3b34c,0xac57ae8d,0xb0f3b1d2,0x3249317d,0xb400b3ef,0x1d1ba810,0xadd4aff3,0x337332f1,
  0xb39cb3e3,0x2cf32953,0xa500ab28,0x33fa33cc,0xae99b0f8,0x334a3245,0x33ff33b2,0x201f2c63,0x2438a9b6,0x33fc33df,0x332c33d2,0xaf15aac6,
  0x303a2ce7,0x32cb339e,0x30a83219,0xb281b12e,0x32ee31c0,0x2ffe3190,0x28292ddf,0xb3efb371,0x33b0327e,0x2c6f30ad,0xb241b035,0xb0fdb2ce,
  0x335933fc,0xae54a406,0xb400b392,0x1b11ad2f,0x2f5931da,0xb31bb174,0xb21db37f,0x31292d99,0xaaad2842,0xb3d3b3ee,0xa9cfb005,0x33de32eb,
  0x285b305f,0xb3edb2b3,0x2c0ea9e8,0x33bd33dd,0xb170accf,0xb1dfb3a1,0x33453124,0x2eaf3221,0xb3fcb36c,0x23a7adf7,0x33323400,0xaeff997f,
  0xb0b2b304,0x327a2fb2,0x2b713102,0xb3c8b23d,0xb400b2e5,0x17dbb00f,0x2e023264,0xb36ab0d1,0xaf6fb2d5,0x3316302a,0xb11fa8f0,0xb225b3e7,
  0x307f2343,0x329e33fd,0xb3d6b38e,0x2a7cad46,0x33f53342,0xa6c32ebb,0xac87b1e3,0x33ac316b,0x28d7af7a,0x33e83313,0xb2d8b3f7,0x3025a5fb,
  0x33eb31af,0x288d31a1,0x2bebae0e,0x33c03368,0x2ec6330a,0xb33faf9b,0x33fe3235,0x21b1310c,0xb1f4aa63,0xb158b3d7,0x2d5232a2,0xb38bb07a,
  0x33a7333d,0xacab2ed2,0x33f63162,0x262d31eb,0xaa4b301a,0xb3d8b2de,0x2a32326b,0xb3d9b0c7,0xb3f6b26f,0x265fb0c1,0xb3a9b020,0xac9fb2db,
  0x0e48b15d,0x340031f0,0xae1ab33a,0x33652edd,0xaed22e25,0xb33db363,0xb1eb0e48,0xb162b400,0xb2deb3a7,0x301aacab,0xb0c7b3f6,0x326b262d,
  0x30c1aa4b,0x326f33d8,0x32db2a32,0x302033d9,0x31f033f6,0xb15d265f,0x2edd33a9,0xb33aac9f,0xb2acb385,0x306aad76,0x2a19b166,0x33da31e7,
  0x3229a2de,0x311b33fd,0x33133337,0xaf7a2ee8,0x2e3133c5,0xb360aba2,0xb1a128d7,0xb1afb3e8,0xb3f5b015,0xa691b2e1,0xaf9bb3eb,0x330a288d,
  0x3154acc3,0x31f833a3,0x2ef433f8,0xb335a5c9,0x2d8133dc,0xb383aa01,0xb3feb065,0x214db2b0,0xb3ecb107,0x2874b239,0x300fafa6,0x32e53307,
  0x30b7ae3c,0x3276335e,0x302a3400,0xb2d517db,0x312433bd,0xb2212c0e,0xb318b260,0x2f64b0d6,0xb400aeaf,0x997fb345,0x335c20e8,0x2e4833fe,
  0x3102aeff,0x323d3332,0xac7b31fc,0xb3aeb14f,0x2a9433c8,0xb3d4ab71,0xb084b3e6,0x329ba909,0xb2ce2aad,0xb035b3d3,0x33e529cf,0x292233de,
  0x2d2fb241,0x339230fd,0xb14a2fbd,0xb200b301,0x2d993400,0xb37f1b11,0x2084b36f,0x33ff2deb,0xb2ebb21d,0x3005b129,0x30db339f,0xb25c2cdb,
  0xae5fb3e4,0x3357a93b,0xb190303a,0xb1c0b2cb,0x32453258,0xb0f830e0,0x2c63b2ee,0x33b22ffe,0xb3dfae99,0x29b6b34a,0x2ac633ff,0xb3d2a01f,
  0x339ea438,0x2ce733fc,0xb12eb32c,0x3219af15,0x33b8a78b,0x2c3233f2,0x2810b3b3,0x33ef2c57,0xb2c72e6b,0xb040b354,0x29533400,0xb3e31d1b,
  0x3141b133,0x32093215,0xaf21b39c,0x332aacf3,0xae8d32bd,0xb34cb050,0x317d3290,0xb1d23094,0x27bd33fb,0xb3f1249c,0x2fdd3327,0xb2f72f2c,
  0xaaf7b3e2,0x33cfa96c,0xb099b2c4,0x328cb045,0x2cff33b7,0xb39a2c3e,0x31373250,0xb21130ea,0xae76b378,0x3352adbc,0xb1c9b1cd,0x3186b182,
  0xb3ff1ead,0x1de4b3ff,0xb352adbc,0x2e76b378,0x33f1249c,0xa7bd33fb,0x32f72f2c,0xafdd3327,0xb3cfa96c,0x2af7b3e2,0xb28cb045,0x3099b2c4,
  0x339a2c3e,0xacff33b7,0x321130ea,0xb1373250,0x2953b400,0x33e31d1b,0x33ccadd4,0x2b283373,0xaf21339c,0xb32aacf3,0xb3fb2500,0x246ab3fa,
  0x317db290,0x31d23094,0x337a2ade,0xadb133d0,0xb2f130f3,0xaff3b249,0xb254afd2,0x30e5b2fb,0x339e2438,0xace733fc,0xb12e332c,0xb219af15,
  0xb190b03a,0x31c0b2cb,0x3371b0a8,0x2ddf3281,0x2c6332ee,0xb3b22ffe,0xb3f22829,0x2759b3ef,0x2ac6b3ff,0x33d2a01f,0x32932da5,0xb08e337c,
  0xaf0a33f3,0xb32fa727,0x2406b3b0,0x33fcac6f,0x3347b194,0x2ea431bc,0xb1743359,0xb1daae54,0xb3bc2565,0x2c1ab3f9,0x33eeaf59,0x2842331b,
  0x30ad3089,0xb27e3297,0xb2ceaaad,0x3035b3d3,0xb29ba909,0x3084b3e6,0x305f3030,0xb2b332d1,0x259732e8,0xb3f8300a,0x2ccfb3ed,0x33a1a85b,
  0x31b8b381,0x31992d8d,0xb36c31df,0xadf7b170,0xb3f42d3a,0x26f5b390,0x330423a7,0xafb233fc,0x316bb3d6,0x31e32a7c,0xb3832a01,0x2d81b3dc,
  0xb3bf2c87,0x2c02b3ac,0x28743239,0xb3ec3107,0x2b8931b3,0xb3c6319d,0x3276b35e,0x30b72e3c,0x31f8b3a3,0x31542cc3,0xb33525c9,0x2ef4b3f8,
  0x310c2beb,0xb23533c0,0x33abb267,0x2c9330cc,0x307ab3fe,0x32a2a1b1,0xb06aad76,0x32acb385,0xb3a52d52,0x2cb7b38b,0xb11b33fd,0xb229a2de,
  0x94b63273,0xb40030bc,0x3360aba2,0xae3133c5,0xb2de33a7,0xb01aacab,0xb0c733f6,0xb26b262d,0x30c12a4b,0xb26f33d8,0x32dbaa32,0xb02033d9,
  0x31f0b3f6,0x315d265f,0x2eddb3a9,0x333aac9f,0xb1eb8e48,0x3162b400,0xb3872e1a,0x2d6ab365,0xae25ad5e,0x3363b389,0x8e48b15d,0x3400b1f0,
  0xb3a7333d,0xacabaed2,0xb3f63162,0x262db1eb,0x2a4b301a,0xb3d832de,0xaa32326b,0xb3d930c7,0x33f6b26f,0x265f30c1,0x33a9b020,0xac9f32db,
  0x33c0b368,0x2beb2e0e,0x30cc94b6,0xb2673400,0x21b1b10c,0x33feb235,0x3385b3ab,0x2d762c93,0xb38b307a,0x2d52b2a2,0xa2deb06a,0x33fdb2ac,
  0xb0bc33a5,0xb2732cb7,0xb3c5311b,0x2ba2b229,0x26c32ebb,0xb3f53342,0xb3ac316b,0x2c87b1e3,0x336ab0d1,0xae023264,0xb19d33bf,0xb1b32c02,
  0x3225b3e7,0x311fa8f0,0x2cc32b89,0xb3a333c6,0xaa7cad46,0x33d6b38e,0x33dcb1f8,0xaa013154,0xb3fe3318,0x20e8af64,0x3381b3f8,0x2d8d2597,
  0xb14f335c,0xb1fc2e48,0x2d3ab199,0x3390b1b8,0x29092c7b,0xb3e633ae,0xb03026f5,0x32d1b3f4,0x32e8b084,0xb00a329b,0xb3ed32b3,0x285bb05f,
  0x29cfb005,0x33deb2eb,0xb05a325c,0xb2b630db,0xafbd2922,0x3301b3e5,0x27272b59,0xb3f333c9,0xb36f3200,0x2debb14a,0x31bcaf0a,0xb194332f,
  0xb39f33ff,0xacdba084,0x33f9b347,0xa5652ea4,0x3394b2ba,0xad233055,0xa438a9b6,0x33fcb3df,0x33e4b3f9,0x293b2533,0xb03a2ce7,0x32cbb39e,
  0x3258b357,0x30e0ae5f,0xb2ee31c0,0x2ffeb190,0x2e99b0f8,0x334ab245,0xb3ff33b2,0x201fac63,0xaf4230a3,0xb3213285,0x3133b040,0xb21532c7,
  0xa99e2d17,0xb3e03396,0x32bdb209,0xb0503141,0x278b1f76,0xb3f233ff,0x33b3b34c,0xac572e8d,0x2e6bac32,0xb35433b8,0x3400b3ef,0x1d1b2810,
  0xb289324d,0x309eb0ee,0xb3ce33b5,0x2b0fac4b,0xb2f432c1,0x2fe8b04a,0xb3f033e1,0x27efa985,0xb34f3324,0x2e82af37,0xb3ff33fa,0x1eada4ce,
  0xb3983376,0x2d0badc8,0xb3fb33ff,0xa49c1de4,0x351c35f6,0xac93a617,0xb8a3b93c,0x308d2a16,0x32f43448,0xb160afa5,0xb6a4b7fe,0x353a3389,
  0x2fa53160,0xb448b2f4,0xb389b53a,0x37fe36a4,0x26172c93,0xb5f6b51c,0xaa16b08d,0x393c38a3,0x34c3358c,0xac47a5b2,0xb85fb8f3,0x304229b1,
  0x327e33fd,0xb106af26,0xb63cb785,0x34e7330f,0x2f263106,0xb3fdb27e,0xb30fb4e7,0x3785363c,0x25b22c47,0xb58cb4c3,0xa9b1b042,0x38f3385f,
  0x346a3523,0xabf6a54d,0xb81ab8a8,0x2fef294d,0x3209336b,0xb0acaea7,0xb5d4b70a,0x34933294,0x2ea730ac,0xb36bb209,0xb294b493,0x370a35d4,
  0x254d2bf6,0xb523b46a,0xa94dafef,0x38a8381a,0x341334bc,0xab5fa4e9,0xb7a6b85a,0x2f5928e8,0x319432da,0xb052ae28,0xb56ab68d,0x343e3219,
  0x2e283052,0xb2dab194,0xb219b43e,0x368d356a,0x24e92b5f,0xb4bcb413,0xa8e8af59,0x385a37a6,0x33783456,0xaac8a484,0xb715b80a,0x2ec32884,
  0x3120324a,0xaff2ada9,0xb4ffb60e,0x33d3319e,0x2da92ff2,0xb24ab120,0xb19eb3d3,0x360e34ff,0x24842ac8,0xb456b378,0xa884aec3,0x380a3715,
  0x32cd33e3,0xaa31a420,0xb682b76f,0x2e2d281f,0x30ac31bb,0xaf3fad2a,0xb493b58d,0x33283122,0x2d2a2f3f,0xb1bbb0ac,0xb122b328,0x358d3493,
  0x24202a31,0xb3e3b2cd,0xa81fae2d,0x376f3682,0x3223331c,0xa999a376,0xb5ebb6c6,0x2d972776,0x3039312d,0xae8dacac,0xb426b50b,0x327c30a6,
  0x2cac2e8d,0xb12db039,0xb0a6b27c,0x350b3426,0x23762999,0xb31cb223,0xa776ad97,0x36c635eb,0x317a3257,0xa902a2ad,0xb552b61a,0x2d0026ad,
  0x2f8c309f,0xaddcac2e,0xb371b487,0x31cf3029,0x2c2e2ddc,0xb09faf8c,0xb029b1cf,0x34873371,0x22ad2902,0xb257b17a,0xa6adad00,0x361a3552,
  0x30d23194,0xa86ba1e4,0xb4b7b56a,0x2c6a25e4,0x2ea73012,0xad2aab5f,0xb294b402,0x31222f59,0x2b5f2d2a,0xb012aea7,0xaf59b122,0x34023294,
  0x21e4286b,0xb194b0d2,0xa5e4ac6a,0x356a34b7,0x302c30d2,0xa7a9a11b,0xb41ab4b7,0x2ba7251b,0x2dc22f0c,0xac79aa63,0xb1b6b2f7,0x30742e5f,
  0x2a632c79,0xaf0cadc2,0xae5fb074,0x32f731b6,0x211b27a9,0xb0d2b02c,0xa51baba7,0x34b7341a,0x2f0c3012,0xa67ba052,0xb2f7b402,0x2a7a2452,
  0x2cde2df5,0xab91a967,0xb0d7b1e8,0x2f8b2d65,0x29672b91,0xadf5acde,0xad65af8b,0x31e830d7,0x2052267b,0xb012af0c,0xa452aa7a,0x340232f7,
  0x2dc22ea7,0xa54d9f12,0xb1b6b294,0x294d2311,0x2bf62cde,0xaa31a86b,0xafefb0d7,0x2e2d2c6a,0x286b2a31,0xacdeabf6,0xac6aae2d,0x30d72fef,
  0x1f12254d,0xaea7adc2,0xa311a94d,0x329431b6,0x2c792d2a,0xa4209d7f,0xb074b122,0x281f217f,0x2a312b91,0xa8d0a6e0,0xae2daf8b,0x2cce2ade,
  0x26e028d0,0xab91aa31,0xaadeacce,0x2f8b2e2d,0x1d7f2420,0xad2aac79,0xa17fa81f,0x31223074,0x2a632b5f,0xa1e49bdb,0xae5faf59,0x25e41fdb,
  0x286b2967,0xa6e0a4e9,0xac6aad65,0x2ade28e8,0x24e926e0,0xa967a86b,0xa8e8aade,0x2d652c6a,0x1bdb21e4,0xab5faa63,0x9fdba5e4,0x2f592e5f,
  0x27a9286b,0x9f1298b6,0xaba7ac6a,0x23111cb6,0x254d267b,0xa420a1e4,0xa94daa7a,0x281f25e4,0x21e42420,0xa67ba54d,0xa5e4a81f,0x2a7a294d,
  0x18b61f12,0xa86ba7a9,0x9cb6a311,0x2c6a2ba7,0x211b21e4,0x98b69248,0xa51ba5e4,0x1cb61648,0x1f122052,0x9d7f9bdb,0xa311a452,0x217f1fdb,
  0x1bdb1d7f,0xa0529f12,0x9fdba17f,0x24522311,0x124818b6,0xa1e4a11b,0x96489cb6,0x25e4251b,0xa11ba1e4,0x18b61248,0x251b25e4,0x9cb69648,
  0x9f12a052,0x1d7f1bdb,0x23112452,0xa17f9fdb,0x9bdb9d7f,0x20521f12,0x1fdb217f,0xa452a311,0x924898b6,0x21e4211b,0x16481cb6,0xa5e4a51b,
  0xa7a9a86b,0x1f1218b6,0x2ba72c6a,0xa3119cb6,0xa54da67b,0x242021e4,0x294d2a7a,0xa81fa5e4,0xa1e4a420,0x267b254d,0x25e4281f,0xaa7aa94d,
  0x98b69f12,0x286b27a9,0x1cb62311,0xac6aaba7,0xaa63ab5f,0x21e41bdb,0x2e5f2f59,0xa5e49fdb,0xa86ba967,0x26e024e9,0x2c6a2d65,0xaadea8e8,
  0xa4e9a6e0,0x2967286b,0x28e82ade,0xad65ac6a,0x9bdba1e4,0x2b5f2a63,0x1fdb25e4,0xaf59ae5f,0xac79ad2a,0x24201d7f,0x30743122,0xa81fa17f,
  0xaa31ab91,0x28d026e0,0x2e2d2f8b,0xacceaade,0xa6e0a8d0,0x2b912a31,0x2ade2cce,0xaf8bae2d,0x9d7fa420,0x2d2a2c79,0x217f281f,0xb122b074,
  0xadc2aea7,0x254d1f12,0x31b63294,0xa94da311,0xabf6acde,0x2a31286b,0x2fef30d7,0xae2dac6a,0xa86baa31,0x2cde2bf6,0x2c6a2e2d,0xb0d7afef,
  0x9f12a54d,0x2ea72dc2,0x2311294d,0xb294b1b6,0xaf0cb012,0x267b2052,0x32f73402,0xaa7aa452,0xacdeadf5,0x2b912967,0x30d731e8,0xaf8bad65,
  0xa967ab91,0x2df52cde,0x2d652f8b,0xb1e8b0d7,0xa052a67b,0x30122f0c,0x24522a7a,0xb402b2f7,0xb02cb0d2,0x27a9211b,0x341a34b7,0xaba7a51b,
  0xadc2af0c,0x2c792a63,0x31b632f7,0xb074ae5f,0xaa63ac79,0x2f0c2dc2,0x2e5f3074,0xb2f7b1b6,0xa11ba7a9,0x30d2302c,0x251b2ba7,0xb4b7b41a,
  0xb0d2b194,0x286b21e4,0x34b7356a,0xac6aa5e4,0xaea7b012,0x2d2a2b5f,0x32943402,0xb122af59,0xab5fad2a,0x30122ea7,0x2f593122,0xb402b294,
  0xa1e4a86b,0x319430d2,0x25e42c6a,0xb56ab4b7,0xb17ab257,0x290222ad,0x3552361a,0xad00a6ad,0xaf8cb09f,0x2ddc2c2e,0x33713487,0xb1cfb029,
  0xac2eaddc,0x309f2f8c,0x302931cf,0xb487b371,0xa2ada902,0x3257317a,0x26ad2d00,0xb61ab552,0xb223b31c,0x29992376,0x35eb36c6,0xad97a776,
  0xb039b12d,0x2e8d2cac,0x3426350b,0xb27cb0a6,0xacacae8d,0x312d3039,0x30a6327c,0xb50bb426,0xa376a999,0x331c3223,0x27762d97,0xb6c6b5eb,
  0xb2cdb3e3,0x2a312420,0x3682376f,0xae2da81f,0xb0acb1bb,0x2f3f2d2a,0x3493358d,0xb328b122,0xad2aaf3f,0x31bb30ac,0x31223328,0xb58db493,
  0xa420aa31,0x33e332cd,0x281f2e2d,0xb76fb682,0xb378b456,0x2ac82484,0x3715380a,0xaec3a884,0xb120b24a,0x2ff22da9,0x34ff360e,0xb3d3b19e,
  0xada9aff2,0x324a3120,0x319e33d3,0xb60eb4ff,0xa484aac8,0x34563378,0x28842ec3,0xb80ab715,0xb413b4bc,0x2b5f24e9,0x37a6385a,0xaf59a8e8,
  0xb194b2da,0x30522e28,0x356a368d,0xb43eb219,0xae28b052,0x32da3194,0x3219343e,0xb68db56a,0xa4e9ab5f,0x34bc3413,0x28e82f59,0xb85ab7a6,
  0xb46ab523,0x2bf6254d,0x381a38a8,0xafefa94d,0xb209b36b,0x30ac2ea7,0x35d4370a,0xb493b294,0xaea7b0ac,0x336b3209,0x32943493,0xb70ab5d4,
  0xa54dabf6,0x3523346a,0x294d2fef,0xb8a8b81a,0xb4c3b58c,0x2c4725b2,0x385f38f3,0xb042a9b1,0xb27eb3fd,0x31062f26,0x363c3785,0xb4e7b30f,
  0xaf26b106,0x33fd327e,0x330f34e7,0xb785b63c,0xa5b2ac47,0x358c34c3,0x29b13042,0xb8f3b85f,0xb51cb5f6,0x2c932617,0x38a3393c,0xb08daa16,
  0xb2f4b448,0x31602fa5,0x36a437fe,0xb53ab389,0xafa5b160,0x344832f4,0x3389353a,0xb7feb6a4,0xa617ac93,0x35f6351c,0x2a16308d,0xb93cb8a3,
};
__device__ __align__(128) const uint32_t c_img[2560] = {
  0x326d31ed,0x333b32dd,0x33c33388,0x33fe33ea,0x33c331ed,0x31ed33c3,0xa8b22d64,0xb33bb0c4,0x33ea31ed,0xad64301d,0xb2ddb388,0x315fa8b2,
  0x32dd31ed,0xb3feabc6,0x326dad64,0xad64326d,0x30c431ed,0xaed7b2dd,0x2bc63388,0xa248b3ea,0x2bc631ed,0x315fb3c3,0xb3ea2d64,0x2ed730c4,
  0xa8b231ed,0x3388b01d,0x301db388,0xb1ed28b2,0xb01d31ed,0x22482bc6,0x30c4ad64,0x3388b26d,0x33ea33fe,0x338833c3,0x32dd333b,0x31ed326d,
  0xb2ddb3fe,0xa248b01d,0x326d2ed7,0x338833ea,0x30c433fe,0xb33babc6,0xabc6b33b,0x33fe30c4,0xabc6b3fe,0x31ed32dd,0xb3eaaed7,0x333ba8b2,
  0xa8b233fe,0x2d64b3c3,0xb01d333b,0x315fb26d,0x301db3fe,0xb3fe301d,0x30c42ed7,0x2d64b3ea,0xb26d33fe,0x2ed72bc6,0x33c3b33b,0xa248b0c4,
  0x33c3b3fe,0x315fb2dd,0x28b2aed7,0xaed728b2,0xb0c4b15f,0xaed7b01d,0xabc6ad64,0xa248a8b2,0xabc6b15f,0x315f2bc6,0x33ea3388,0x2ed7326d,
  0x28b2b15f,0x338832dd,0xb01d2d64,0xb1edb3ea,0x301db15f,0x224833c3,0xb0c4b388,0x338830c4,0x326db15f,0xb33b301d,0x33c3ad64,0xb3fe28b2,
  0x33c3b15f,0xb1edabc6,0xa8b23388,0x333bb26d,0x33eab15f,0x2d64b2dd,0xb2dd2d64,0xb15f33ea,0x32ddb15f,0x33feb3c3,0x326db388,0x2d64b0c4,
  0x28b22248,0x2d642bc6,0x301d2ed7,0x315f30c4,0xb01da248,0xb3feb2dd,0xb0c4b33b,0x2d64a8b2,0x326d2248,0x2ed733c3,0xb3c3aed7,0xa248b26d,
  0xb3c3a248,0x315fb01d,0xa8b2333b,0xaed7b3ea,0x33ea2248,0xb388abc6,0x32dd2ed7,0xb1edb0c4,0xb2dda248,0x224832dd,0x326db33b,0xb38828b2,
  0x30c42248,0x333bb3c3,0xabc6aed7,0xb3fe326d,0xabc6a248,0xb1ed301d,0xb3ea333b,0xb33b33ea,0xb26d31ed,0xb33b32dd,0xb3c33388,0xb3fe33ea,
  0xb3c331ed,0xb1ed33c3,0x28b22d64,0x333bb0c4,0xb3ea31ed,0x2d64301d,0x32ddb388,0xb15fa8b2,0xb2dd31ed,0x33feabc6,0xb26dad64,0x2d64326d,
  0xb0c431ed,0x2ed7b2dd,0xabc63388,0x2248b3ea,0xabc631ed,0xb15fb3c3,0x33ea2d64,0xaed730c4,0x28b231ed,0xb388b01d,0xb01db388,0x31ed28b2,
  0x301d31ed,0xa2482bc6,0xb0c4ad64,0xb388b26d,0xb3ea33fe,0xb38833c3,0xb2dd333b,0xb1ed326d,0x32ddb3fe,0x2248b01d,0xb26d2ed7,0xb38833ea,
  0xb0c433fe,0x333babc6,0x2bc6b33b,0xb3fe30c4,0x2bc6b3fe,0xb1ed32dd,0x33eaaed7,0xb33ba8b2,0x28b233fe,0xad64b3c3,0x301d333b,0xb15fb26d,
  0xb01db3fe,0x33fe301d,0xb0c42ed7,0xad64b3ea,0x326d33fe,0xaed72bc6,0xb3c3b33b,0x2248b0c4,0xb3c3b3fe,0xb15fb2dd,0xa8b2aed7,0x2ed728b2,
  0x30c4b15f,0x2ed7b01d,0x2bc6ad64,0x2248a8b2,0x2bc6b15f,0xb15f2bc6,0xb3ea3388,0xaed7326d,0xa8b2b15f,0xb38832dd,0x301d2d64,0x31edb3ea,
  0xb01db15f,0xa24833c3,0x30c4b388,0xb38830c4,0xb26db15f,0x333b301d,0xb3c3ad64,0x33fe28b2,0xb3c3b15f,0x31edabc6,0x28b23388,0xb33bb26d,
  0xb3eab15f,0xad64b2dd,0x32dd2d64,0x315f33ea,0xb2ddb15f,0xb3feb3c3,0xb26db388,0xad64b0c4,0xa8b22248,0xad642bc6,0xb01d2ed7,0xb15f30c4,
  0x301da248,0x33feb2dd,0x30c4b33b,0xad64a8b2,0xb26d2248,0xaed733c3,0x33c3aed7,0x2248b26d,0x33c3a248,0xb15fb01d,0x28b2333b,0x2ed7b3ea,
  0xb3ea2248,0x3388abc6,0xb2dd2ed7,0x31edb0c4,0x32dda248,0xa24832dd,0xb26db33b,0x338828b2,0xb0c42248,0xb33bb3c3,0x2bc6aed7,0x33fe326d,
  0x2bc6a248,0x31ed301d,0x33ea333b,0x333b33ea,0x30c4315f,0x2ed7301d,0x2bc62d64,0x224828b2,0x2bc6315f,0xb15fabc6,0xb3eab388,0xaed7b26d,
  0xa8b2315f,0xb388b2dd,0x301dad64,0x31ed33ea,0xb01d315f,0xa248b3c3,0x30c43388,0xb388b0c4,0xb26d315f,0x333bb01d,0xb3c32d64,0x33fea8b2,
  0xb3c3315f,0x31ed2bc6,0x28b2b388,0xb33b326d,0xb3ea315f,0xad6432dd,0x32ddad64,0x315fb3ea,0xb2dd315f,0xb3fe33c3,0xb26d3388,0xad6430c4,
  0xa8b2a248,0xad64abc6,0xb01daed7,0xb15fb0c4,0x301d2248,0x33fe32dd,0x30c4333b,0xad6428b2,0xb26da248,0xaed7b3c3,0x33c32ed7,0x2248326d,
  0x33c32248,0xb15f301d,0x28b2b33b,0x2ed733ea,0xb3eaa248,0x33882bc6,0xb2ddaed7,0x31ed30c4,0x32dd2248,0xa248b2dd,0xb26d333b,0x3388a8b2,
  0xb0c4a248,0xb33b33c3,0x2bc62ed7,0x33feb26d,0x2bc62248,0x31edb01d,0x33eab33b,0x333bb3ea,0x326d31ed,0x333b32dd,0x33c33388,0x33fe33ea,
  0x33c331ed,0x31ed33c3,0xa8b22d64,0xb33bb0c4,0x33ea31ed,0xad64301d,0xb2ddb388,0x315fa8b2,0x32dd31ed,0xb3feabc6,0x326dad64,0xad64326d,
  0x30c431ed,0xaed7b2dd,0x2bc63388,0xa248b3ea,0x2bc631ed,0x315fb3c3,0xb3ea2d64,0x2ed730c4,0xa8b231ed,0x3388b01d,0x301db388,0xb1ed28b2,
  0xb01d31ed,0x22482bc6,0x30c4ad64,0x3388b26d,0x33ea33fe,0x338833c3,0x32dd333b,0x31ed326d,0xb2ddb3fe,0xa248b01d,0x326d2ed7,0x338833ea,
  0x30c433fe,0xb33babc6,0xabc6b33b,0x33fe30c4,0xabc6b3fe,0x31ed32dd,0xb3eaaed7,0x333ba8b2,0xa8b233fe,0x2d64b3c3,0xb01d333b,0x315fb26d,
  0x301db3fe,0xb3fe301d,0x30c42ed7,0x2d64b3ea,0xb26d33fe,0x2ed72bc6,0x33c3b33b,0xa248b0c4,0x33c3b3fe,0x315fb2dd,0x28b2aed7,0xaed728b2,
  0xb0c4315f,0xaed7301d,0xabc62d64,0xa24828b2,0xabc6315f,0x315fabc6,0x33eab388,0x2ed7b26d,0x28b2315f,0x3388b2dd,0xb01dad64,0xb1ed33ea,
  0x301d315f,0x2248b3c3,0xb0c43388,0x3388b0c4,0x326d315f,0xb33bb01d,0x33c32d64,0xb3fea8b2,0x33c3315f,0xb1ed2bc6,0xa8b2b388,0x333b326d,
  0x33ea315f,0x2d6432dd,0xb2ddad64,0xb15fb3ea,0x32dd315f,0x33fe33c3,0x326d3388,0x2d6430c4,0x28b2a248,0x2d64abc6,0x301daed7,0x315fb0c4,
  0xb01d2248,0xb3fe32dd,0xb0c4333b,0x2d6428b2,0x326da248,0x2ed7b3c3,0xb3c32ed7,0xa248326d,0xb3c32248,0x315f301d,0xa8b2b33b,0xaed733ea,
  0x33eaa248,0xb3882bc6,0x32ddaed7,0xb1ed30c4,0xb2dd2248,0x2248b2dd,0x326d333b,0xb388a8b2,0x30c4a248,0x333b33c3,0xabc62ed7,0xb3feb26d,
  0xabc62248,0xb1edb01d,0xb3eab33b,0xb33bb3ea,0xb26d31ed,0xb33b32dd,0xb3c33388,0xb3fe33ea,0xb3c331ed,0xb1ed33c3,0x28b22d64,0x333bb0c4,
  0xb3ea31ed,0x2d64301d,0x32ddb388,0xb15fa8b2,0xb2dd31ed,0x33feabc6,0xb26dad64,0x2d64326d,0xb0c431ed,0x2ed7b2dd,0xabc63388,0x2248b3ea,
  0xabc631ed,0xb15fb3c3,0x33ea2d64,0xaed730c4,0x28b231ed,0xb388b01d,0xb01db388,0x31ed28b2,0x301d31ed,0xa2482bc6,0xb0c4ad64,0xb388b26d,
  0xb3ea33fe,0xb38833c3,0xb2dd333b,0xb1ed326d,0x32ddb3fe,0x2248b01d,0xb26d2ed7,0xb38833ea,0xb0c433fe,0x333babc6,0x2bc6b33b,0xb3fe30c4,
  0x2bc6b3fe,0xb1ed32dd,0x33eaaed7,0xb33ba8b2,0x28b233fe,0xad64b3c3,0x301d333b,0xb15fb26d,0xb01db3fe,0x33fe301d,0xb0c42ed7,0xad64b3ea,
  0x326d33fe,0xaed72bc6,0xb3c3b33b,0x2248b0c4,0xb3c3b3fe,0xb15fb2dd,0xa8b2aed7,0x2ed728b2,0x29ed29ed,0x29ed29ed,0x29ed29ed,0x29ed29ed,
  0x2bc32a6d,0x2add2bea,0x23c628c4,0xa81da0b2,0x2bc32add,0xa3c6281d,0xabc3aadd,0x23c6a81d,0x29ed2b3b,0xabfea564,0x295fa6d7,0x1a482b88,
  0x25642b88,0xa564ab88,0x25642b88,0xa564ab88,0xa0b22bc3,0x2a6daadd,0xabea23c6,0x28c4281d,0xa8c42bea,0x2a6da0b2,0x28c4abea,0xaa6d20b2,
  0xab3b2bfe,0xa564295f,0x26d79a48,0x2b88a9ed,0x29ed29ed,0x29ed29ed,0x29ed29ed,0x29ed29ed,0xabc3aa6d,0xaaddabea,0xa3c6a8c4,0x281d20b2,
  0x2bc32add,0xa3c6281d,0xabc3aadd,0x23c6a81d,0xa9edab3b,0x2bfe2564,0xa95f26d7,0x9a48ab88,0x25642b88,0xa564ab88,0x25642b88,0xa564ab88,
  0x20b2abc3,0xaa6d2add,0x2beaa3c6,0xa8c4a81d,0xa8c42bea,0x2a6da0b2,0x28c4abea,0xaa6d20b2,0x2b3babfe,0x2564a95f,0xa6d71a48,0xab8829ed,
  0x295f295f,0x295f295f,0x295f295f,0x295f295f,0x23c628c4,0xa81da0b2,0xabc3aa6d,0xaaddabea,0xa3c6281d,0xabc3aadd,0x23c6a81d,0x2bc32add,
  0xa95f26d7,0x9a48ab88,0x29ed2b3b,0xabfea564,0xab882564,0x2b88a564,0xab882564,0x2b88a564,0xabea23c6,0x28c4281d,0x20b2abc3,0xaa6d2add,
  0xaa6d20b2,0xa8c42bea,0x2a6da0b2,0x28c4abea,0xa6d71a48,0xab8829ed,0xab3b2bfe,0xa564295f,0x295f295f,0x295f295f,0x295f295f,0x295f295f,
  0xa3c6a8c4,0x281d20b2,0x2bc32a6d,0x2add2bea,0xa3c6281d,0xabc3aadd,0x23c6a81d,0x2bc32add,0x295fa6d7,0x1a482b88,0xa9edab3b,0x2bfe2564,
  0xab882564,0x2b88a564,0xab882564,0x2b88a564,0x2beaa3c6,0xa8c4a81d,0xa0b22bc3,0x2a6daadd,0xaa6d20b2,0xa8c42bea,0x2a6da0b2,0x28c4abea,
  0x26d79a48,0x2b88a9ed,0x2b3babfe,0x2564a95f,0xabfe2bfe,0xabfe2bfe,0xabfe2bfe,0xabfe2bfe,0xaadd2bea,0xa3c628c4,0x281da0b2,0x2bc3aa6d,
  0xa81d2bc3,0x2adda3c6,0x281dabc3,0xaadd23c6,0x9a482b88,0x29edab3b,0xabfe2564,0x295f26d7,0x26d72b3b,0xa6d7ab3b,0x26d72b3b,0xa6d7ab3b,
  0x2a6d2add,0xabeaa3c6,0x28c4a81d,0x20b22bc3,0x2bea2a6d,0xa0b228c4,0xabeaaa6d,0x20b2a8c4,0x2b8829ed,0x2b3b2bfe,0x2564295f,0xa6d79a48,
  0xabfe2bfe,0xabfe2bfe,0xabfe2bfe,0xabfe2bfe,0x2addabea,0x23c6a8c4,0xa81d20b2,0xabc32a6d,0xa81d2bc3,0x2adda3c6,0x281dabc3,0xaadd23c6,
  0x1a48ab88,0xa9ed2b3b,0x2bfea564,0xa95fa6d7,0x26d72b3b,0xa6d7ab3b,0x26d72b3b,0xa6d7ab3b,0xaa6daadd,0x2bea23c6,0xa8c4281d,0xa0b2abc3,
  0x2bea2a6d,0xa0b228c4,0xabeaaa6d,0x20b2a8c4,0xab88a9ed,0xab3babfe,0xa564a95f,0x26d71a48,0x1a489a48,0x1a489a48,0x1a489a48,0x1a489a48,
  0x281da0b2,0x2bc3aa6d,0x2addabea,0x23c6a8c4,0x2adda3c6,0x281dabc3,0xaadd23c6,0xa81d2bc3,0x2bfea564,0xa95fa6d7,0x9a482b88,0x29edab3b,
  0x2b3ba6d7,0xab3b26d7,0x2b3ba6d7,0xab3b26d7,0x28c4a81d,0x20b22bc3,0xaa6daadd,0x2bea23c6,0x20b2a8c4,0x2bea2a6d,0xa0b228c4,0xabeaaa6d,
  0xa564a95f,0x26d71a48,0x2b8829ed,0x2b3b2bfe,0x1a489a48,0x1a489a48,0x1a489a48,0x1a489a48,0xa81d20b2,0xabc32a6d,0xaadd2bea,0xa3c628c4,
  0x2adda3c6,0x281dabc3,0xaadd23c6,0xa81d2bc3,0xabfe2564,0x295f26d7,0x1a48ab88,0xa9ed2b3b,0x2b3ba6d7,0xab3b26d7,0x2b3ba6d7,0xab3b26d7,
  0xa8c4281d,0xa0b2abc3,0x2a6d2add,0xabeaa3c6,0x20b2a8c4,0x2bea2a6d,0xa0b228c4,0xabeaaa6d,0x2564295f,0xa6d79a48,0xab88a9ed,0xab3babfe,
  0xa95fa95f,0xa95fa95f,0xa95fa95f,0xa95fa95f,0xa3c6a8c4,0x281d20b2,0x2bc32a6d,0x2add2bea,0x23c6a81d,0x2bc32add,0xa3c6281d,0xabc3aadd,
  0x295fa6d7,0x1a482b88,0xa9edab3b,0x2bfe2564,0x2b88a564,0xab882564,0x2b88a564,0xab882564,0x2beaa3c6,0xa8c4a81d,0xa0b22bc3,0x2a6daadd,
  0x2a6da0b2,0x28c4abea,0xaa6d20b2,0xa8c42bea,0x26d79a48,0x2b88a9ed,0x2b3babfe,0x2564a95f,0xa95fa95f,0xa95fa95f,0xa95fa95f,0xa95fa95f,
  0x23c628c4,0xa81da0b2,0xabc3aa6d,0xaaddabea,0x23c6a81d,0x2bc32add,0xa3c6281d,0xabc3aadd,0xa95f26d7,0x9a48ab88,0x29ed2b3b,0xabfea564,
  0x2b88a564,0xab882564,0x2b88a564,0xab882564,0xabea23c6,0x28c4281d,0x20b2abc3,0xaa6d2add,0x2a6da0b2,0x28c4abea,0xaa6d20b2,0xa8c42bea,
  0xa6d71a48,0xab8829ed,0xab3b2bfe,0xa564295f,0x29ed29ed,0x29ed29ed,0x29ed29ed,0x29ed29ed,0x2bc32a6d,0x2add2bea,0x23c628c4,0xa81da0b2,
  0x2bc32add,0xa3c6281d,0xabc3aadd,0x23c6a81d,0x29ed2b3b,0xabfea564,0x295fa6d7,0x1a482b88,0x25642b88,0xa564ab88,0x25642b88,0xa564ab88,
  0xa0b22bc3,0x2a6daadd,0xabea23c6,0x28c4281d,0xa8c42bea,0x2a6da0b2,0x28c4abea,0xaa6d20b2,0xab3b2bfe,0xa564295f,0x26d79a48,0x2b88a9ed,
  0x29ed29ed,0x29ed29ed,0x29ed29ed,0x29ed29ed,0xabc3aa6d,0xaaddabea,0xa3c6a8c4,0x281d20b2,0x2bc32add,0xa3c6281d,0xabc3aadd,0x23c6a81d,
  0xa9edab3b,0x2bfe2564,0xa95f26d7,0x9a48ab88,0x25642b88,0xa564ab88,0x25642b88,0xa564ab88,0x20b2abc3,0xaa6d2add,0x2beaa3c6,0xa8c4a81d,
  0xa8c42bea,0x2a6da0b2,0x28c4abea,0xaa6d20b2,0x2b3babfe,0x2564a95f,0xa6d71a48,0xab8829ed,0x9a481a48,0x9a481a48,0x9a481a48,0x9a481a48,
  0xa81d20b2,0xabc32a6d,0xaadd2bea,0xa3c628c4,0xaadd23c6,0xa81d2bc3,0x2adda3c6,0x281dabc3,0xabfe2564,0x295f26d7,0x1a48ab88,0xa9ed2b3b,
  0xab3b26d7,0x2b3ba6d7,0xab3b26d7,0x2b3ba6d7,0xa8c4281d,0xa0b2abc3,0x2a6d2add,0xabeaa3c6,0xa0b228c4,0xabeaaa6d,0x20b2a8c4,0x2bea2a6d,
  0x2564295f,0xa6d79a48,0xab88a9ed,0xab3babfe,0x9a481a48,0x9a481a48,0x9a481a48,0x9a481a48,0x281da0b2,0x2bc3aa6d,0x2addabea,0x23c6a8c4,
  0xaadd23c6,0xa81d2bc3,0x2adda3c6,0x281dabc3,0x2bfea564,0xa95fa6d7,0x9a482b88,0x29edab3b,0xab3b26d7,0x2b3ba6d7,0xab3b26d7,0x2b3ba6d7,
  0x28c4a81d,0x20b22bc3,0xaa6daadd,0x2bea23c6,0xa0b228c4,0xabeaaa6d,0x20b2a8c4,0x2bea2a6d,0xa564a95f,0x26d71a48,0x2b8829ed,0x2b3b2bfe,
  0xabfe2bfe,0xabfe2bfe,0xabfe2bfe,0xabfe2bfe,0xaadd2bea,0xa3c628c4,0x281da0b2,0x2bc3aa6d,0xa81d2bc3,0x2adda3c6,0x281dabc3,0xaadd23c6,
  0x9a482b88,0x29edab3b,0xabfe2564,0x295f26d7,0x26d72b3b,0xa6d7ab3b,0x26d72b3b,0xa6d7ab3b,0x2a6d2add,0xabeaa3c6,0x28c4a81d,0x20b22bc3,
  0x2bea2a6d,0xa0b228c4,0xabeaaa6d,0x20b2a8c4,0x2b8829ed,0x2b3b2bfe,0x2564295f,0xa6d79a48,0xabfe2bfe,0xabfe2bfe,0xabfe2bfe,0xabfe2bfe,
  0x2addabea,0x23c6a8c4,0xa81d20b2,0xabc32a6d,0xa81d2bc3,0x2adda3c6,0x281dabc3,0xaadd23c6,0x1a48ab88,0xa9ed2b3b,0x2bfea564,0xa95fa6d7,
  0x26d72b3b,0xa6d7ab3b,0x26d72b3b,0xa6d7ab3b,0xaa6daadd,0x2bea23c6,0xa8c4281d,0xa0b2abc3,0x2bea2a6d,0xa0b228c4,0xabeaaa6d,0x20b2a8c4,
  0xab88a9ed,0xab3babfe,0xa564a95f,0x26d71a48,0x3bfb3bff,0x3be53bf2,0x3bbf3bd4,0x3b873ba5,0x3bd03bfb,0x3b013b7c,0x399d3a60,0x378538bc,
  0x35173b52,0xbbc9b7c8,0xb074ba9b,0x3bfe391b,0x319e3b27,0xbbf3b979,0x363cb80a,0x3a2d3bc5,0xba093986,0x3a7eb8f8,0xbae5385f,0x3b3db77a,
  0xbabd393c,0x3bb0b699,0xbc00305b,0x3ba730d7,0xbb2a35c8,0xb8353bb2,0x3a64b1e8,0x3962bbf7,0xba90350b,0xba413bff,0x3602340e,0x3bf6bad8,
  0xac6aa5e4,0xb122af59,0xb402b294,0xb56ab4b7,0xb2deac9c,0xb7bdb5a5,0xb9b3b8d6,0xbb10ba73,0xbb96b676,0xb359bafe,0x3bec3884,0x2a163a29,
  0xbbe0b72c,0x2f27b9d6,0x3b5e3ae8,0xb91633a2,0xb941b9c9,0x38ad3a45,0xb80fbab3,0x36d23b13,0xb850ba0d,0x346f3b4a,0x1fdbbbed,0xb4ab3be8,
  0x3721bb76,0xbace3463,0xb8d13bdd,0x39ebadfb,0x3894bb98,0xb8fd281f,0xbb6a3bbd,0x2e2d3825,0x3b3f3b65,0x3ae83b16,0x3a813ab6,0x3a0d3a49,
  0x3263356a,0xad972b43,0xb5dfb359,0xb8eeb7f3,0xa9b139aa,0xbbedba25,0x3340b889,0x3b983afb,0xbaa2aa16,0xb4cfbb8e,0x3c0038ad,0xb44b38e5,
  0xbb853625,0x3bbdb4c3,0xbbe432ad,0x3bfbaf8b,0xbaacb6d2,0x39243954,0xb65fbace,0x2fbd3bb8,0xb9661648,0xba603bf8,0x383a31cf,0x3b27bbb3,
  0x3219b9eb,0xbb1836f4,0xb9903be5,0x37dd3010,0xb6c6b61a,0xb80ab76f,0xb8a8b85a,0xb93cb8f3,0xbbd7bb87,0xbbf8bbfd,0xbb71bbc9,0xba4dbaf1,
  0xbbfeb9a6,0x305bb91f,0x3bcb3a97,0xb50b37d2,0xb87abbfe,0x3ba13546,0x24523a7e,0xbbb5ba54,0xb576bb63,0x340e3ba3,0xb13bbbd3,0x2c9c3bf2,
  0x386abb3d,0xba2139f8,0x3b57b835,0xbbf13432,0x39e7bc00,0xb8d6adc9,0xbacb3bde,0x372c3457,0x3bdab962,0x3764bb35,0xb9c03122,0xbaf73bef,
  0x398b39cd,0x38fd3946,0x386538b2,0x37853815,0xba85b9c9,0xbb92bb1e,0xbbfebbdd,0xbbc2bbf5,0xb66b3682,0xbb01bb94,0x387fb371,0x3a2d3beb,
  0xbac7bb76,0x3a00ad33,0x36bb3bd4,0xbbeab79b,0xbc0026ad,0x3bf32c38,0xbbd6b109,0x3ba733eb,0x3153bbff,0xb70a3b9e,0x396bba9b,0xbade390c,
  0xb5d4b5bc,0xbbb03b2c,0x32013830,0x3bf6ba67,0x3bccbb52,0x2c06b92e,0xbb83385f,0xb8c73bab,0xb9c5b982,0xba41ba04,0xbab0ba7a,0xbb10bae1,
  0xb8a3b986,0xb52fb74e,0xa94db1e8,0x33d32e91,0xbb54bb4f,0x37bdb523,0x3a9e3bc8,0xb916308d,0x3840b5c8,0x394a3bf9,0xbb42b294,0xb0a6bb0a,
  0x251bbbff,0xaf273bfc,0x327cbbe6,0xb4ab3bc0,0x3be325e4,0xbb2fb4e7,0x39e33884,0xb81aba35,0x3b73bb78,0xb46fb715,0xbbdc3ad1,0x2e2d38cc,
  0x33283676,0x3bfcba19,0x3581bab3,0xba6b3493,0x363136dd,0x34cf3581,0x32c6341a,0x2fbd3153,0xbae1bb65,0xb970ba39,0xb715b889,0xb16cb4f3,
  0xb9a12a7a,0xb924bbfe,0x3a933042,0x37dd3bcc,0x308db9aa,0x3b453b07,0xb94632ad,0xb845bbfa,0xbb68b55e,0x3b1836bb,0xbabab805,0x3a4d38a3,
  0x3bc0b625,0xbbfe2ec3,0x3b9431cf,0xba89b742,0x9cb6b95d,0xbbf8396b,0xb1b63a5c,0x3bb5b840,0x38cc9648,0x3b81bbac,0xac38b85a,0xbbce3933,
  0xbb60bb3a,0xbba1bb83,0xbbd2bbbc,0xbbf1bbe3,0x3815361a,0x39df3907,0x3b2c3a97,0x3be23b9c,0xb9afbbfd,0x3a21294d,0x388e3bee,0xbaf7b328,
  0x3beb39a6,0xb6af37a6,0xba04bbd3,0x3ac42d00,0x360ebb89,0xb7643b42,0x3855baeb,0xb8ee3a85,0x33eb3b63,0x28e8bbf5,0xb5233bde,0x389ebb21,
  0x3c00b9f0,0x2d97b9e3,0xbbdf38db,0xb44b3ac7,0xba673c00,0x358d3487,0x3bfcbab6,0x330fba15,0x3b7a3bf1,0x394a3a93,0x33893764,0xb3d39cb6,
  0x3afb3be2,0x35eb3946,0xb4c328e8,0xbaa9b8cc,0x27763af7,0xbb2fbaba,0x3a76ad97,0x30a63b60,0xaf8b3ac4,0xb994bb94,0x3bf8358d,0xb8743815,
  0xbb4c38ee,0x3bfcb1b6,0xbad5b4cf,0x381a39af,0xbbb3389e,0x3b592c38,0xb76fb970,0xb24b3beb,0xb9d2344b,0xbb923bd2,0xb0f03924,0x3a6bb60e,
  0xb8f3330f,0xbc003b2c,0xb91f3b45,0x323233eb,0xb5b1afbd,0xba00b88e,0xbbc6bb18,0xbbc2bc00,0xb7d2b16c,0xbb6fba04,0xbba3bbfe,0xb86fba67,
  0xbbffb7dd,0x370ab855,0x38b73bf8,0xbbeab631,0xbbf2b845,0x39bcb523,0x2dc93b81,0xbaa5bae1,0xb68dba4d,0xac063bdf,0x382abba1,0xbade39a1,
  0xb457ba89,0xb6543bfc,0x3b16b9df,0xbbd8308d,0x397dbbb5,0xb52fb2c6,0xbbe73a21,0xb8c73b68,0x3a49bbce,0x2311b715,0xba2536af,0xbbd93bc0,
  0xb958b785,0xbb81ba9e,0xbbefbbf3,0xba89bb73,0xbbf7bbc2,0xb9b8bb42,0xaf59b70a,0x384a3328,0xbb8bba2d,0x39dfb27c,0x34263bb0,0xbbceb98b,
  0xb4b7bbea,0x3b6c39e3,0xbafe2c06,0x3185ba85,0xaadebba7,0xb6af3bdc,0x3a58ba41,0xbbe2366b,0x3a29bade,0xbc003581,0x3a45352f,0xb2f7bac7,
  0x3b37bbf6,0x28e8b865,0xbaee37bd,0xbac43c00,0x3b13b8c7,0x3b5cbbfe,0x3463b94a,0xb8993153,0xb9f4bb10,0xb58db87f,0x3029af27,0x389e35d4,
  0x2dfbb3d3,0x399936bb,0x3bf23b2f,0x3ac13bcc,0x3552b916,0x39703bd6,0xbbbab46f,0x330fb9c5,0x3ba530a6,0xb5f7396b,0xb7c8bbfc,0x3be138a3,
  0x3bfdb4ab,0xbb45b201,0x38e038fd,0xb16cbb54,0x391b381a,0xa17fbb83,0xb8f83b92,0x3bcfb840,0x36e82e2d,0x3bfebab0,0x37febb01,0xb845251b,
  0xb77a3a6b,0x3648294d,0x3bb2ba00,0x3a8cbbe3,0xb742b93c,0x2311b340,0x37a6340e,0x3aa93966,0x3b963a4d,0x3b7f3c00,0x380f3a21,0xb0be3219,
  0x3933b50b,0x35eb3be4,0xbbf5b8d6,0x3874b6c6,0x39413bb5,0xbbffb65f,0x38d1b764,0x33ba3bd7,0x3b9c2c9c,0xb994b83a,0x34873ae8,0x324bbbfe,
  0xb7213bf1,0x3b47b990,0xbbbf2d97,0x38c1387a,0x2d00372c,0x3b59b8a8,0x3a39bbed,0xb232b576,0xbbfb3af7,0xb9743b71,0x307434cf,0x3adbb86a,
  0x3b213a0d,0x3c003bcb,0x3b073bbd,0x386f39e7,0x351738ee,0xb599a452,0xbae5b924,0xbbe9bbda,0x3a153b98,0xbb6fb13b,0x2ec3ba60,0x3aa53b3f,
  0xba09344b,0xa884bb57,0x3a643b18,0xbbc3b263,0xb4f33bfb,0x39bcbacb,0xbbac380a,0x3bd8a9b1,0xbb2aafbd,0x36a439c0,0x3402bbf8,0xba6f3aa2,
  0xbbfa3b27,0xb6543a81,0x3907b05b,0x3bd9bb85,0x2c6ab7dd,0xb9da35df,0xbbec3ba1,0xb8203aac,0x3bf53b87,0x3b6c3bec,0x392e3a7e,0x32f73721,
  0xb9e7b785,0xbbfcbb5e,0xba81bbb0,0xb43eb894,0x379b3bfe,0xbc00b80f,0x374eb835,0x38993bfb,0xbb3fba2d,0x3b329fdb,0xb3403a41,0xb8eabbd0,
  0xb90c3b3d,0x3b5cb8d1,0xbbf93122,0x3ac13517,0x29b1bba7,0xb94f3b6a,0x3be4b7bd,0xbaf4b19e,0xbbab3962,0xb9993bbf,0x34e73359,0x3be1ba09,
  0x3b85bbf6,0x353ab99d,0xb83a2f27,0xbbf03abd,0x2e91356a,0xb5f7b074,0xba19b8ad,0xbbcfbb2a,0xb966bb10,0xaba7b63c,0x38a8346f,0x3bb73a90,
  0xbb0aaa16,0xa17fbae5,0x3b1e3ace,0xba8c2c6a,0x36c6b916,0x36ff3c00,0xbbcbb8fd,0x3a50b2de,0xba35b6d2,0x36483a64,0x2d33bbe5,0xb84a3b96,
  0x3bfeb4ab,0xb9fcb602,0x313b3b01,0x37e8bbe0,0x3493b9eb,0xb9b83402,0xbb9e3bc9,0xb1853941,0x35762e2d,0x3b90b9b3,0x3acbbbf3,0x2fefb850,
  0x3a543bcf,0x2884374e,0xb9f8b648,0xbbe9bbab,0x398b3bb7,0xb4db3340,0xbbdcb9fc,0xb911bb85,0xb4323a8c,0xb6a4bbf9,0x3b3539b8,0xbbc3ae91,
  0xb66b3a50,0xad65bbe4,0x38653b90,0xbb0db966,0xbbef384a,0x39da34e7,0x2b43bb6c,0xba6f3b0a,0xbc0037e8,0x3759383a,0x387fbbfc,0xbbf636c6,
  0xb7f33185,0xbb7f3a19,0xbb8e3c00,0xb8203a35,0xb5d42fef,0xba1d38a8,0xbbd63b32,0xbba93bfe,0xb8e5b2f7,0xbbffbb1e,0xb954bb5c,0x30beb493,
  0xb9c5b43e,0xbb9fbbcb,0xb201b94f,0x3a313576,0xbbb8b899,0x3b47ad33,0xb6f43999,0xb3babbf5,0xbb54b8ea,0x3bf9313b,0xbab0353a,0x3790b9e7,
  0xb010bac1,0xb9743b9e,0x3bfdb5f7,0xb8c1b79b,0x251bbaf4,0xbb1b3acb,0x3a9e2ba7,0x2e5fbb3f,0x3af1bbe1,0x3599b92e,0xb546a17f,0xbadb390c,
  0x3b73bbf0,0x3929ba81,0x327cb6ff,0xb49f29b1,0xb825baa9,0x353aaec3,0x3b7c3994,0x3af43bfa,0x360eb0be,0x3bf43a64,0x388e3b47,0xb7372c6a,
  0x38bcb874,0x2ba73bac,0xb979bb59,0x3bf03742,0x3c0033ba,0xbb043402,0x3855b974,0xacce3b96,0x3bc5b24b,0xb6ffb907,0xb6993c00,0x3bb7b933,
  0x363138c1,0x3902bbec,0xbbdf3599,0x34ff3941,0x30d73232,0x39fcb7a6,0x3bffbb6f,0x3a50bb9c,0xb9a13adb,0xb47b380f,0x32c62884,0x3937b721,
  0x3ad8386f,0x3b903bf5,0x35a539bc,0xb7e8ad00,0x3b683be9,0x2ef538d1,0xba93b6a4,0xbb24bbfb,0x3a733aa5,0xbbfcb487,0x39d6b654,0xafef3b21,
  0x1cb63bc3,0xb7b2bbbf,0x3aba39da,0xbbfab517,0xb3a23bd8,0x3b32ba39,0xbb4a2311,0x343e3a15,0xbb603a6f,0x3a3d3074,0x31b6bb7f,0xbb9a3a09,
  0xbbe83bd9,0xb94f3b07,0xa81f35eb,0x38eab4f3,0xb9af3820,0xbbae3ae5,0xbbd23bff,0xba113b2a,0x319e389e,0xb929b426,0xbc00bb45,0xb911bb37,
  0xbbffbac1,0xb805bafe,0x382a217f,0x3bfd3b13,0xbabd330f,0x34dbba58,0x36023bfe,0xbb0db9f4,0xb68dbbe1,0x3a5c3a45,0xbbe7b648,0x3b89adfb,
  0xba90b16c,0x2d653aee,0x39b3bb81,0xbbf63552,0x397dbbcf,0xbbbc3463,0x338939b8,0x39f0bba5,0x32deb845,0xb7593029,0xbb5e39df,0xbba93bfd,
  0x3b7aba8c,0x3beebbf2,0x3a76bb6c,0x36ddb91b,0xbbe0ba89,0xba1dbbba,0x1fdbb6af,0x3a3136e8,0xa776b84a,0x3aeb37c8,0x3ad53c00,0xaa7a377a,
  0xb850bbce,0x3b9f38e0,0xbb6a28e8,0x3790b958,0x3b4cb185,0xb8db38f8,0x30f0bb5c,0x355e3bf7,0x3894bbe2,0xbbf937fe,0x399d358d,0x2e5fbb8b,
  0x39d232f7,0x341abbb2,0xbbc63999,0x395d34b7,0x3bd0bac4,0x3b1bbbef,0x363cb970,0xb49faade,0xb5b13899,0x30422f59,0x38b7b5f7,0x3b3aba29,
  0x3219b3d3,0x3b0438b7,0x3b713bfc,0x34ff397d,0x36e83aa9,0xb8b2adc9,0xbbefbb59,0xb5bcba49,0x3bd730a6,0xb902382a,0xa452bb92,0x39373b7a,
  0xb9583874,0x3371bb16,0x34263c00,0xb982bafb,0x387a381a,0x347bbbe7,0xbb573a00,0x3b242776,0xbb8b324b,0x31093a25,0x3a58bb6f,0xbb4f2f8b,
  0xb86a3a6b,0x2ef53389,0x39c0b70a,0x3bfabb4c,0xaadeb232,0xb83034c3,0xbaee39bc,0xbbff3bb3,0x3bda3bc2,0x37b23a76,0xb5df2c06,0xbb9ab9d2,
  0xbb37b86f,0xba7abbf8,0x3029b654,0x3b7838f3,0x32633bea,0xba3dbad5,0x3c00352f,0xba1135b1,0xb9f4baa5,0x3bc8376f,0xbbba2311,0x39cdb7d2,
  0xbaa23ade,0x3baeb0f0,0xb65fb94a,0xb7373bff,0x3552bbd8,0xbbe6391f,0x38e035eb,0x3682bbf2,0xbaac38c7,0xbbf43bc6,0xb9903b2f,0xacce368d,
  0x3bfdbbd9,0x3ad1bba3,0x37feb994,0x26adb457,0x38a33b9a,0xb8dba452,0xbb83bbae,0x2a7ab86a,0x37423b78,0xbab6b426,0xb907bbe6,0x39aa2ade,
  0xb8403a11,0x341abb57,0x294d3bf4,0xb55ebbda,0xb93339cd,0x3889ba58,0xb7a63ad1,0x3625bb37,0xbbe33737,0x304239c0,0x3b42bb04,0xb95db263,
  0xbb9c3682,0xb2ad3aee,0x3bf5b8b2,0x1648b9f4,0xb3282cce,0xb80535df,0xb9e33902,0xbb3a3aa2,0xad0026ad,0xb1cf3029,0xb4873371,0xb61a3552,
  0xba85b4ff,0xba5cbc00,0x3581b47b,0x3bfd3aac,0xbb21b5bc,0xb85abbba,0x3a393109,0x39a63bfd,0xbac7b937,0x3bbc365f,0xbbfeaef5,0x3b89b219,
  0xba15b982,0x3a9738e0,0xbb07b830,0x3b6336e8,0x3153bb24,0xbbee3990,0x36bb37b2,0x39f0bbd7,0x34f3bb4f,0xbbd337fe,0xaec33a7a,0x3c00b958,
  0x3bccbbfa,0x3aebbb71,0x396bba3d,0x36ddb87a,0x3bfabbff,0x3bdebbef,0x3bacbbc8,0x3b65bb8b,0x3bc03911,0x38303b6a,0xb946ad65,0xbb4fbbd0,
  0x3a353bfd,0xb85f30f0,0xbb1ebbbc,0x35c8b5b1,0x38cc3b0d,0xba7ab99d,0x3b943759,0xbbffb19e,0xb4933b89,0x31e8bbc6,0xad333bee,0xa5e4bbff,
  0xb8153bf6,0x3bc8b63c,0xac38ba1d,0xbb783abd,0xbbf539f0,0x329438b7,0x3b9ebaeb,0xb676b68d,0xbbeb3ba9,0xbbe63c00,0xbb2c3b9f,0xb9cd3a90,
  0xb79b36dd,0xb884382a,0xb92e38db,0xb9c9397d,0x33eb3a31,0xbad1b602,0xba04bbf9,0x3682b2de,0xb90c2a7a,0xbab3bbe7,0x374eb41a,0x3b763b7a,
  0xba673790,0x38b2b9b3,0xb5233b1b,0x26adbbe0,0xbbabb55e,0x3bdd3389,0xbbf9b042,0x3bff2776,0xbae12e5f,0xb3713b5e,0x3bfcb929,0xb5bcb850,
  0xae91b95d,0xbbd43a76,0x34e73805,0x3b52bb4c,0x308db49f,0xb1091fdb,0xb71534db,0xb9823894,0x3b0abb3a,0x3a9bbad5,0x3a19ba5c,0x3986b9d2,
  0x2f8bb7e8,0x3bde3979,0x376f3b32,0xb9aab0d7,0x3bb83b24,0xb1223855,0xbbfdba3d,0xaa16b9a1,0x3bb3afef,0xbab63699,0x391fb94f,0xb6253ad8,
  0x30103bfa,0xb359bbdf,0x35463bae,0xb6d2bb68,0x38f3343e,0x3889bbff,0xbba3353a,0x96483a73,0xbaf13b9a,0x38ad32c6,0x39f8bbf4,0xb9eb9cb6,
  0xb7d238ea,0xb2ad35a5,0x2dc92ba7,0x361ab3a2,0xba543a11,0xbace3a93,0xbb353b04,0xbb873b60,0x3bf23af4,0x31cf39d6,0xbb16b6ff,0xb9a6bbe8,
  0xb4323737,0xbbe5baba,0x2b43b902,0x3bfe39af,0x34573bf0,0xb85abb4a,0x3a2539fc,0xbb63b825,0xbbef2cce,0x3bc9b1b6,0xbb8e347b,0x3b3db60e,
  0xba493bb7,0x3a97a81f,0x34c3bb90,0xbc0038bc,0xb7f3b4ff,0xba7e3bd2,0x39542ef5,0x3962bc00,0xbafb3a50,0xbbd33b7c,0xbbf83bfc,0xbb653bc5,
  0x38e5b937,0x3835b88e,0x36f4b7b2,0x356ab631,0xbb13bbe9,0x31e8b6f4,0x3bf239da,0x36763af1,0x3be83911,0x340e3ab0,0xbb7cb759,0xb72cbb73,
  0x2dfbbbc3,0x32943bfd,0xb7c8bb7f,0x39c93a54,0x38253b0d,0xb8d6ba9e,0x39793a1d,0xba0db98b,0x3ba5ba6f,0xb884b546,0xb8f83bff,0x3b76b432,
  0xb8bc3bf6,0x3ae8b27c,0x3699bb9f,0xbb98366b,0x391bb820,0x3ab3b9f8,0x3bb2bb47,0x3bffbbef,0xbbc53ba9,0xbbed3bdc,0xbbff3bf9,0xbbfb3c00,
  0x377ab0be,0x3bdd3b35,0x2f593974,0xbb52b7f3,0x30d73a31,0xbbbdb865,0xb5a5bb1b,0x3b2735d4,0x3bf733ba,0xbbd42b43,0x3afeb599,0xb98638e5,
  0xbad83790,0x3a60b87f,0xb9d63929,0x393cb9c5,0x34b738c1,0x3a9bbb8e,0xba45a884,0xb5c83bb8,0xba732e5f,0xb80a3bd6,0x3b4ab4db,0x350bbb54,
  0xba293adb,0xb85f3954,0xb46336a4,0x25e43010,0x33a2b49f,0x305bb201,0x281fad65,0xac9c251b,0x3f803f80,0x3f803f80,0x3f803f80,0x3f803f80,
  0x3f803f80,0x3f803f80,0x3f803f80,0x3f803f80,0x3f803f80,0x3f803f80,0x3f803f80,0x3f803f80,0x3f803f80,0x3f803f80,0x3f803f80,0x3f803f80,
  0x3f803f80,0x3f803f80,0x3f803f80,0x3f803f80,0x3f803f80,0x3f803f80,0x3f803f80,0x3f803f80,0x3f803f80,0x3f803f80,0x3f803f80,0x3f803f80,
  0x3f803f80,0x3f803f80,0x3f803f80,0x3f803f80,0x3f803f80,0x3f803f80,0x3f803f80,0x3f803f80,0x3f803f80,0x3f803f80,0x3f803f80,0x3f803f80,
  0x3f803f80,0x3f803f80,0x3f803f80,0x3f803f80,0x3f803f80,0x3f803f80,0x3f803f80,0x3f803f80,0x3f803f80,0x3f803f80,0x3f803f80,0x3f803f80,
  0x3f803f80,0x3f803f80,0x3f803f80,0x3f803f80,0x3f803f80,0x3f803f80,0x3f803f80,0x3f803f80,0x3f803f80,0x3f803f80,0x3f803f80,0x3f803f80,
  0x3f803f80,0x3f803f80,0x3f803f80,0x3f803f80,0x3f803f80,0x3f803f80,0x3f803f80,0x3f803f80,0x3f803f80,0x3f803f80,0x3f803f80,0x3f803f80,
  0x3f803f80,0x3f803f80,0x3f803f80,0x3f803f80,0x3f803f80,0x3f803f80,0x3f803f80,0x3f803f80,0x3f803f80,0x3f803f80,0x3f803f80,0x3f803f80,
  0x3f803f80,0x3f803f80,0x3f803f80,0x3f803f80,0x3f803f80,0x3f803f80,0x3f803f80,0x3f803f80,0x3f803f80,0x3f803f80,0x3f803f80,0x3f803f80,
  0x3f803f80,0x3f803f80,0x3f803f80,0x3f803f80,0x3f803f80,0x3f803f80,0x3f803f80,0x3f803f80,0x3f803f80,0x3f803f80,0x3f803f80,0x3f803f80,
  0x3f803f80,0x3f803f80,0x3f803f80,0x3f803f80,0x3f803f80,0x3f803f80,0x3f803f80,0x3f803f80,0x3f803f80,0x3f803f80,0x3f803f80,0x3f803f80,
  0x3f803f80,0x3f803f80,0x3f803f80,0x3f803f80,0x3f803f80,0x3f803f80,0x3f803f80,0x3f803f80,0x3f803f80,0x3f803f80,0x3f803f80,0x3f803f80,
  0x3f803f80,0x3f803f80,0x3f803f80,0x3f803f80,0x3f803f80,0x3f803f80,0x3f803f80,0x3f803f80,0x3f803f80,0x3f803f80,0x3f803f80,0x3f803f80,
  0x3f803f80,0x3f803f80,0x3f803f80,0x3f803f80,0x3f803f80,0x3f803f80,0x3f803f80,0x3f803f80,0x3f803f80,0x3f803f80,0x3f803f80,0x3f803f80,
  0x3f803f80,0x3f803f80,0x3f803f80,0x3f803f80,0x3f803f80,0x3f803f80,0x3f803f80,0x3f803f80,0x3f803f80,0x3f803f80,0x3f803f80,0x3f803f80,
  0x3f803f80,0x3f803f80,0x3f803f80,0x3f803f80,0x3f803f80,0x3f803f80,0x3f803f80,0x3f803f80,0x3f803f80,0x3f803f80,0x3f803f80,0x3f803f80,
  0x3f803f80,0x3f803f80,0x3f803f80,0x3f803f80,0x3f803f80,0x3f803f80,0x3f803f80,0x3f803f80,0x3f803f80,0x3f803f80,0x3f803f80,0x3f803f80,
  0x3f803f80,0x3f803f80,0x3f803f80,0x3f803f80,0x3f803f80,0x3f803f80,0x3f803f80,0x3f803f80,0x3f803f80,0x3f803f80,0x3f803f80,0x3f803f80,
  0x3f803f80,0x3f803f80,0x3f803f80,0x3f803f80,0x3f803f80,0x3f803f80,0x3f803f80,0x3f803f80,0x3f803f80,0x3f803f80,0x3f803f80,0x3f803f80,
  0x3f803f80,0x3f803f80,0x3f803f80,0x3f803f80,0x3f803f80,0x3f803f80,0x3f803f80,0x3f803f80,0x3f803f80,0x3f803f80,0x3f803f80,0x3f803f80,
  0x3f803f80,0x3f803f80,0x3f803f80,0x3f803f80,0x3f803f80,0x3f803f80,0x3f803f80,0x3f803f80,0x3f803f80,0x3f803f80,0x3f803f80,0x3f803f80,
  0x3f803f80,0x3f803f80,0x3f803f80,0x3f803f80,0x3f803f80,0x3f803f80,0x3f803f80,0x3f803f80,0x3f803f80,0x3f803f80,0x3f803f80,0x3f803f80,
  0x3f803f80,0x3f803f80,0x3f803f80,0x3f803f80,0x3f803f80,0x3f803f80,0x3f803f80,0x3f803f80,0x3f803f80,0x3f803f80,0x3f803f80,0x3f803f80,
  0x3f803f80,0x3f803f80,0x3f803f80,0x3f803f80,0x3f803f80,0x3f803f80,0x3f803f80,0x3f803f80,0x3f803f80,0x3f803f80,0x3f803f80,0x3f803f80,
  0x3f803f80,0x3f803f80,0x3f803f80,0x3f803f80,0x3f803f80,0x3f803f80,0x3f803f80,0x3f803f80,0x3f803f80,0x3f803f80,0x3f803f80,0x3f803f80,
  0x3f803f80,0x3f803f80,0x3f803f80,0x3f803f80,0x3f803f80,0x3f803f80,0x3f803f80,0x3f803f80,0x3f803f80,0x3f803f80,0x3f803f80,0x3f803f80,
  0x3f803f80,0x3f803f80,0x3f803f80,0x3f803f80,0x3f803f80,0x3f803f80,0x3f803f80,0x3f803f80,0x3f803f80,0x3f803f80,0x3f803f80,0x3f803f80,
  0x3f803f80,0x3f803f80,0x3f803f80,0x3f803f80,0x3f803f80,0x3f803f80,0x3f803f80,0x3f803f80,0x3f803f80,0x3f803f80,0x3f803f80,0x3f803f80,
  0x3f803f80,0x3f803f80,0x3f803f80,0x3f803f80,0x3f803f80,0x3f803f80,0x3f803f80,0x3f803f80,0x3f803f80,0x3f803f80,0x3f803f80,0x3f803f80,
  0x3f803f80,0x3f803f80,0x3f803f80,0x3f803f80,0x3f803f80,0x3f803f80,0x3f803f80,0x3f803f80,0x3f803f80,0x3f803f80,0x3f803f80,0x3f803f80,
  0x3f803f80,0x3f803f80,0x3f803f80,0x3f803f80,0x3f803f80,0x3f803f80,0x3f803f80,0x3f803f80,0x3f803f80,0x3f803f80,0x3f803f80,0x3f803f80,
  0x3f803f80,0x3f803f80,0x3f803f80,0x3f803f80,0x3f803f80,0x3f803f80,0x3f803f80,0x3f803f80,0x3f803f80,0x3f803f80,0x3f803f80,0x3f803f80,
  0x3f803f80,0x3f803f80,0x3f803f80,0x3f803f80,0x3f803f80,0x3f803f80,0x3f803f80,0x3f803f80,0x3f803f80,0x3f803f80,0x3f803f80,0x3f803f80,
  0x3f803f80,0x3f803f80,0x3f803f80,0x3f803f80,0x3f803f80,0x3f803f80,0x3f803f80,0x3f803f80,0x3f803f80,0x3f803f80,0x3f803f80,0x3f803f80,
  0x3f803f80,0x3f803f80,0x3f803f80,0x3f803f80,0x3f803f80,0x3f803f80,0x3f803f80,0x3f803f80,0x3f803f80,0x3f803f80,0x3f803f80,0x3f803f80,
  0x3f803f80,0x3f803f80,0x3f803f80,0x3f803f80,0x3f803f80,0x3f803f80,0x3f803f80,0x3f803f80,0x3f803f80,0x3f803f80,0x3f803f80,0x3f803f80,
  0x3f803f80,0x3f803f80,0x3f803f80,0x3f803f80,0x3f803f80,0x3f803f80,0x3f803f80,0x3f803f80,0x3f803f80,0x3f803f80,0x3f803f80,0x3f803f80,
  0x3f803f80,0x3f803f80,0x3f803f80,0x3f803f80,0x3f803f80,0x3f803f80,0x3f803f80,0x3f803f80,0x3f803f80,0x3f803f80,0x3f803f80,0x3f803f80,
  0x3f803f80,0x3f803f80,0x3f803f80,0x3f803f80,0x3f803f80,0x3f803f80,0x3f803f80,0x3f803f80,0x3f803f80,0x3f803f80,0x3f803f80,0x3f803f80,
  0x3f803f80,0x3f803f80,0x3f803f80,0x3f803f80,0x3f803f80,0x3f803f80,0x3f803f80,0x3f803f80,0x3f803f80,0x3f803f80,0x3f803f80,0x3f803f80,
  0x3f803f80,0x3f803f80,0x3f803f80,0x3f803f80,0x3f803f80,0x3f803f80,0x3f803f80,0x3f803f80,0x3f803f80,0x3f803f80,0x3f803f80,0x3f803f80,
  0x3f803f80,0x3f803f80,0x3f803f80,0x3f803f80,0x3f803f80,0x3f803f80,0x3f803f80,0x3f803f80,0x3f803f80,0x3f803f80,0x3f803f80,0x3f803f80,
  0x3f803f80,0x3f803f80,0x3f803f80,0x3f803f80,0x3f803f80,0x3f803f80,0x3f803f80,0x3f803f80,0x3f803f80,0x3f803f80,0x3f803f80,0x3f803f80,
  0x3f803f80,0x3f803f80,0x3f803f80,0x3f803f80,
};

__device__ __align__(128) float    g_part[16][8][2176];
__device__ __align__(128) float    g_kv[16][2176];
__device__ __align__(128) uint4    g_o[16 * 16 * 1024];
__device__ __align__(128) unsigned g_ocnt[16 * 32];
__device__ unsigned g_epoch[128];
#define GSTAMP(role, i) do {} while (0)
#define STAMP(role, i) do {} while (0)
#define PDUMP(role) do {} while (0)
#define PROF_SMEM 0

constexpr int STAGE_BYTES = 57344;
constexpr int OFF_H = 4 * 16384, OFF_VP = 9 * 16384, OFF_SPARE = 10 * 16384;
constexpr int OFF_XT = 172032, XT_STRIDE = 4112;
constexpr int OFF_BAR = 204928, OFF_EPOCH = OFF_BAR + 640, OFF_EX = OFF_BAR + 656, OFF_D = OFF_BAR + 672, OFF_SCALE = OFF_BAR + 704;
constexpr int OFF_F2F = 205824, OFF_F2I = 207872, OFF_F4 = 209920, OFF_ONES = 214016, OFF_KVB = 214016;
constexpr int OFF_STG = 219136, STG_STRIDE = 4352, SMEM_TOTAL = 232192 + PROF_SMEM;
enum { B_FULL1 = 0, B_EMPTY1 = 3, B_Q = 6, B_XRAW = 10, B_XT = 11, B_KV = 12, B_Y = 13, B_PKFREE = 14, B_AFREE = 15,
       B_STG = 18, B_ODONE = 24, B_XFREE = 25, B_FULL2 = 33, B_CONS2 = 49, B_COUNT = 62 };
__host__ __device__ constexpr int bar_count(int i) {
  return i < B_EMPTY1 ? 1 : i < B_Q ? 4 : i == B_XT ? 4 : i == B_KV ? 2 : i == B_Y ? 9 : i == B_PKFREE ? 4
       : (i >= B_AFREE && i < B_STG) ? 16 : i == B_ODONE ? 8 : (i >= B_XFREE && i < B_FULL2) ? 4
       : (i >= B_CONS2 && i <= B_CONS2 + 10) ? 4 : i >= B_CONS2 ? 2 : (i >= B_FULL2 && i < B_FULL2 + 7) ? 2 : 1;
}
__host__ __device__ constexpr uint64_t bar_counts(int r) {
  uint64_t v = 0;
  for (int w = 0; w < 11; w++) v |= (uint64_t)(bar_count(1 + 11 * r + w) - 1) << (4 * w);
  return v;
}
constexpr uint64_t SLOT_A = 0x9645796457964594ull;
constexpr uint64_t SLOT_B = 0x1032810328103276ull;
constexpr int SPIN_LIMIT = 1 << 22;
#define PKV CU_TENSOR_MAP_L2_PROMOTION_L2_128B
#define BPRE B_KV
#define PFD 3
#define PD1 500
#define PD2 300
#define E1C 2
#define OSP 4
#define QPF 4
#define HOLD 14
#define OC0 1
#define OC1 2
#define HSTART 1500
#define PACE 1050
#define OC 1

__device__ __forceinline__ uint32_t smem_u32(const void* p) { return (uint32_t)__cvta_generic_to_shared(p); }
__device__ __forceinline__ void wg_fence() { asm volatile("wgmma.fence.sync.aligned;" ::: "memory"); }
__device__ __forceinline__ void wg_commit() { asm volatile("wgmma.commit_group.sync.aligned;" ::: "memory"); }
template <int N> __device__ __forceinline__ void wg_wait() { asm volatile("wgmma.wait_group.sync.aligned %0;" ::"n"(N) : "memory"); }
template <int N> __device__ __forceinline__ void keep(float (&d)[N]) {
#pragma unroll
  for (int i = 0; i < N; i++) asm volatile("" : "+f"(d[i])::"memory");
}
__device__ __forceinline__ uint64_t mkdesc(uint32_t addr, uint32_t lbo, uint32_t sbo, uint32_t swz) {
  uint32_t lo = ((addr & 0x3FFFF) >> 4) | ((lbo >> 4) << 16), hi = (sbo >> 4) | (swz << 30);
  return ((uint64_t)hi << 32) | lo;
}
__device__ __forceinline__ void mbar_init(uint32_t bar, int cnt) { asm volatile("mbarrier.init.shared::cta.b64 [%0], %1;" ::"r"(bar), "r"(cnt)); }
__device__ __forceinline__ void mbar_expect(uint32_t bar, int bytes) { asm volatile("mbarrier.arrive.expect_tx.shared::cta.b64 _, [%0], %1;" ::"r"(bar), "r"(bytes) : "memory"); }
__device__ __forceinline__ void mbar_arrive(uint32_t bar) { asm volatile("mbarrier.arrive.shared::cta.b64 _, [%0];" ::"r"(bar) : "memory"); }
__device__ __forceinline__ void mbar_arrive_cl(uint32_t bar, uint32_t cta) {
  asm volatile("{\n.reg .b32 r;\nmapa.shared::cluster.u32 r, %0, %1;\nmbarrier.arrive.shared::cluster.b64 _, [r];\n}\n" ::"r"(bar), "r"(cta) : "memory");
}
__device__ __forceinline__ void mbar_wait(uint32_t bar, uint32_t parity) {
  asm volatile("{\n.reg .pred p;\n.reg .u32 n;\nmov.u32 n, 0;\n"
               "W_%=:\nmbarrier.try_wait.parity.shared::cta.b64 p, [%0], %1;\n@p bra D_%=;\n"
               "add.u32 n, n, 1;\nsetp.lt.u32 p, n, %2;\n@p bra W_%=;\ntrap;\nD_%=:\n}\n" ::"r"(bar), "r"(parity), "n"(SPIN_LIMIT) : "memory");
}
__device__ __forceinline__ void fence_async() { asm volatile("fence.proxy.async.shared::cta;" ::: "memory"); }
__device__ __forceinline__ void bar_sync(int id) { asm volatile("bar.sync %0, 128;" ::"r"(id) : "memory"); }
__device__ __forceinline__ void tma2d(uint32_t dst, const CUtensorMap* m, int c0, int c1, uint32_t bar) {
  asm volatile("cp.async.bulk.tensor.2d.shared::cluster.global.mbarrier::complete_tx::bytes [%0], [%1, {%3, %4}], [%2];"
               ::"r"(dst), "l"(m), "r"(bar), "r"(c0), "r"(c1) : "memory");
}
__device__ __forceinline__ void tma2d_mc(uint32_t dst, const CUtensorMap* m, int c0, int c1, uint32_t bar) {
  asm volatile("cp.async.bulk.tensor.2d.shared::cluster.global.mbarrier::complete_tx::bytes.multicast::cluster [%0], [%1, {%3, %4}], [%2], %5;"
               ::"r"(dst), "l"(m), "r"(bar), "r"(c0), "r"(c1), "h"((uint16_t)3) : "memory");
}
__device__ __forceinline__ void tma3d(uint32_t dst, const CUtensorMap* m, int c0, int c1, int c2, uint32_t bar) {
  asm volatile("cp.async.bulk.tensor.3d.shared::cluster.global.mbarrier::complete_tx::bytes [%0], [%1, {%3, %4, %5}], [%2];"
               ::"r"(dst), "l"(m), "r"(bar), "r"(c0), "r"(c1), "r"(c2) : "memory");
}
__device__ __forceinline__ void bulk_ld(uint32_t dst, const void* src, int bytes, uint32_t bar) {
  asm volatile("cp.async.bulk.shared::cluster.global.mbarrier::complete_tx::bytes [%0], [%1], %2, [%3];" ::"r"(dst), "l"(src), "r"(bytes), "r"(bar) : "memory");
}
__device__ __forceinline__ void bulk_ld_mc(uint32_t dst, const void* src, int bytes, uint32_t bar) {
  asm volatile("cp.async.bulk.shared::cluster.global.mbarrier::complete_tx::bytes.multicast::cluster [%0], [%1], %2, [%3], %4;"
               ::"r"(dst), "l"(src), "r"(bytes), "r"(bar), "h"((uint16_t)3) : "memory");
}
__device__ __forceinline__ void tma2d_st(const CUtensorMap* m, uint32_t src, int c0, int c1) {
  asm volatile("cp.async.bulk.tensor.2d.global.shared::cta.bulk_group [%0, {%2, %3}], [%1];" ::"l"(m), "r"(src), "r"(c0), "r"(c1) : "memory");
}
__device__ __forceinline__ void pf_l2(const void* p, int bytes) { asm volatile("cp.async.bulk.prefetch.L2.global [%0], %1;" ::"l"(p), "r"(bytes) : "memory"); }
__device__ __forceinline__ void pf_t2d(const CUtensorMap* m, int c0, int c1) {
  asm volatile("cp.async.bulk.prefetch.tensor.2d.L2.global [%0, {%1, %2}];" ::"l"(m), "r"(c0), "r"(c1) : "memory");
}
__device__ __forceinline__ void pf_t3d(const CUtensorMap* m, int c0, int c1, int c2) {
  asm volatile("cp.async.bulk.prefetch.tensor.3d.L2.global [%0, {%1, %2, %3}];" ::"l"(m), "r"(c0), "r"(c1), "r"(c2) : "memory");
}
__device__ __forceinline__ void ldsm4(uint32_t (&r)[4], uint32_t a) {
  asm volatile("ldmatrix.sync.aligned.m8n8.x4.shared.b16 {%0,%1,%2,%3}, [%4];" : "=r"(r[0]), "=r"(r[1]), "=r"(r[2]), "=r"(r[3]) : "r"(a) : "memory");
}
__device__ __forceinline__ void ldsm4t(uint32_t (&r)[4], uint32_t a) {
  asm volatile("ldmatrix.sync.aligned.m8n8.x4.trans.shared.b16 {%0,%1,%2,%3}, [%4];" : "=r"(r[0]), "=r"(r[1]), "=r"(r[2]), "=r"(r[3]) : "r"(a) : "memory");
}
__device__ __forceinline__ void stsm4(uint32_t a, uint32_t r0, uint32_t r1, uint32_t r2, uint32_t r3) {
  asm volatile("stmatrix.sync.aligned.m8n8.x4.shared.b16 [%0], {%1,%2,%3,%4};" ::"r"(a), "r"(r0), "r"(r1), "r"(r2), "r"(r3) : "memory");
}
__device__ __forceinline__ uint32_t pk2(float lo, float hi) { uint32_t r; asm("cvt.rn.bf16x2.f32 %0, %1, %2;" : "=r"(r) : "f"(hi), "f"(lo)); return r; }
__device__ __forceinline__ uint32_t hmul(uint32_t a, uint32_t b) { uint32_t r; asm("mul.rn.bf16x2 %0, %1, %2;" : "=r"(r) : "r"(a), "r"(b)); return r; }
__device__ __forceinline__ uint32_t hadd(uint32_t a, uint32_t b) { uint32_t r; asm("add.rn.bf16x2 %0, %1, %2;" : "=r"(r) : "r"(a), "r"(b)); return r; }
__device__ __forceinline__ uint32_t hmax(uint32_t a, uint32_t b) { uint32_t r; asm("max.bf16x2 %0, %1, %2;" : "=r"(r) : "r"(a), "r"(b)); return r; }
__device__ __forceinline__ uint32_t hmin(uint32_t a, uint32_t b) { uint32_t r; asm("min.bf16x2 %0, %1, %2;" : "=r"(r) : "r"(a), "r"(b)); return r; }
__device__ __forceinline__ uint32_t hmaxabs(uint32_t a, uint32_t b) { uint32_t r; asm("max.xorsign.abs.bf16x2 %0, %1, %2;" : "=r"(r) : "r"(a), "r"(b)); return r; }
__device__ __forceinline__ float ex2(float x) { float r; asm("ex2.approx.ftz.f32 %0, %1;" : "=f"(r) : "f"(x)); return r; }
__device__ __forceinline__ float rcp_fast(float x) { float r; asm("rcp.approx.ftz.f32 %0, %1;" : "=f"(r) : "f"(x)); return r; }
__device__ __forceinline__ uint32_t phi2(float lo, float hi) {
  uint32_t t;
  asm("cvt.rn.relu.bf16x2.f32 %0, %1, %2;" : "=r"(t) : "f"(hi), "f"(lo));
  const uint32_t e = pk2(ex2(lo * 1.4426950408889634f), ex2(hi * 1.4426950408889634f));
  return hadd(hadd(t, hmin(e, 0x3F803F80u)), 0x35863586u);
}
__device__ __forceinline__ bool opaque_true() { uint32_t v; asm volatile("mov.u32 %0, %%nctaid.y;" : "=r"(v)); return v != 0; }
__device__ __forceinline__ int normalise(uint32_t (&v)[32], float fd) {
  const float f0 = fd + __uint_as_float(v[0] << 16);
  uint32_t m[4] = {hmaxabs(__float_as_uint(f0) >> 16, v[0]), v[1], v[2], v[3]};
#pragma unroll
  for (int i = 4; i < 32; i++) m[i & 3] = hmaxabs(m[i & 3], v[i]);
  m[0] = hmaxabs(hmaxabs(m[0], m[1]), hmaxabs(m[2], m[3]));
  const int e = min(max((int)(__reduce_max_sync(~0u, max(m[0] & 0x7FFFu, (m[0] >> 16) & 0x7FFFu)) >> 7), 1), 253);
  if (e > 141) {
#pragma unroll
    for (int i = 0; i < 32; i++) v[i] = hmul(v[i], 0x07000700u);
  }
  const uint32_t sc = (e > 141 ? 255 - e : 142 - e) * 0x00800080u;
#pragma unroll
  for (int i = 0; i < 32; i++) {
    const uint32_t a = hmul(v[i], sc);
    v[i] = (a & 0x0FFF0FFFu) * 7 + a;
  }
  v[0] = __byte_perm(v[0], __half_as_ushort(__float2half_rn(f0 * __uint_as_float((254 - e) << 23))), 0x3254);
  return e;
}
__device__ __forceinline__ void poll_ge(const unsigned* p, unsigned target) {
#pragma unroll 1
  for (int n = 0; n < SPIN_LIMIT; n++) {
    unsigned v;
    asm volatile("ld.relaxed.gpu.global.u32 %0, [%1];" : "=r"(v) : "l"(p) : "memory");
    if ((int)(v - target) >= 0) { asm volatile("fence.acquire.gpu;" ::: "memory"); return; }
  }
  __trap();
}

__device__ __forceinline__ bool elect_one() {
  uint32_t p;
  asm volatile("{\n.reg .pred p;\nelect.sync _|p, 0xffffffff;\nselp.u32 %0, 1, 0, p;\n}\n" : "=r"(p));
  return p;
}
__device__ __forceinline__ uint32_t mapa(uint32_t a, uint32_t cta) { uint32_t r; asm("mapa.shared::cluster.u32 %0, %1, %2;" : "=r"(r) : "r"(a), "r"(cta)); return r; }
__device__ __forceinline__ void st_async(uint32_t a, uint32_t v, uint32_t bar) {
  asm volatile("st.async.weak.shared::cluster.mbarrier::complete_tx::bytes.b32 [%0], %1, [%2];" ::"r"(a), "r"(v), "r"(bar) : "memory");
}
__device__ __forceinline__ void st_async4(uint32_t a, uint32_t x, uint32_t y, uint32_t z, uint32_t w, uint32_t bar) {
  asm volatile("st.async.weak.shared::cluster.mbarrier::complete_tx::bytes.v4.b32 [%0], {%1,%2,%3,%4}, [%5];" ::"r"(a), "r"(x), "r"(y), "r"(z), "r"(w), "r"(bar) : "memory");
}
__device__ __forceinline__ void tma3d_st(const CUtensorMap* m, uint32_t src, int c0, int c1, int c2) {
  asm volatile("cp.async.bulk.tensor.3d.global.shared::cta.bulk_group [%0, {%2, %3, %4}], [%1];" ::"l"(m), "r"(src), "r"(c0), "r"(c1), "r"(c2) : "memory");
}
__device__ __forceinline__ uint4 ld_rlx4(const void* p) {
  uint4 v;
  asm volatile("{\n.reg .b128 t;\n.reg .b64 a, b;\nld.relaxed.gpu.global.b128 t, [%4];\nmov.b128 {a, b}, t;\nmov.b64 {%0, %1}, a;\nmov.b64 {%2, %3}, b;\n}\n"
               : "=r"(v.x), "=r"(v.y), "=r"(v.z), "=r"(v.w) : "l"(p) : "memory");
  return v;
}
__device__ __forceinline__ void st_tag4(void* p, float a, float b, float c, float d, uint32_t tag) {
  asm volatile("{\n.reg .b128 t;\n.reg .b64 a, b;\nmov.b64 a, {%1, %2};\nmov.b64 b, {%3, %4};\nmov.b128 t, {a, b};\nst.relaxed.gpu.global.b128 [%0], t;\n}\n"
               ::"l"(p), "r"((__float_as_uint(a) & ~1u) | tag), "f"(b), "f"(c), "f"(d) : "memory");
}
__device__ __forceinline__ uint32_t stale8(const uint4 (&f)[8], uint32_t tag) {
  uint32_t r[4];
#pragma unroll
  for (int i = 0; i < 4; i++) asm("lop3.b32 %0, %1, %2, %3, 0x7E;" : "=r"(r[i]) : "r"(f[2 * i].x), "r"(f[2 * i + 1].x), "r"(tag));
  asm("lop3.b32 %0, %0, %1, %2, 0xFE;" : "+r"(r[0]) : "r"(r[1]), "r"(r[2]));
  return r[0] | r[3];
}

struct ConvC { uint32_t a1[2][4], wa[2], wb[2], sg; };
__device__ __forceinline__ uint64_t dsc(uint32_t lo, uint32_t hi) { return ((uint64_t)hi << 32) | lo; }
__device__ __forceinline__ uint32_t hfma(uint32_t a, uint32_t b, uint32_t c) { uint32_t r; asm("fma.rn.f16x2 %0, %1, %2, %3;" : "=r"(r) : "r"(a), "r"(b), "r"(c)); return r; }
__device__ __forceinline__ uint32_t hfnma(uint32_t a, uint32_t b, uint32_t c) { uint32_t r; asm("{.reg .b32 n; neg.f16x2 n, %1; fma.rn.f16x2 %0, n, %2, %3;}" : "=r"(r) : "r"(a), "r"(b), "r"(c)); return r; }
__device__ __forceinline__ uint32_t hmul16(uint32_t a, uint32_t b) { uint32_t r; asm("mul.rn.f16x2 %0, %1, %2;" : "=r"(r) : "r"(a), "r"(b)); return r; }
template <int N> __device__ __forceinline__ void keepu(uint32_t (&d)[N]) {
#pragma unroll
  for (int i = 0; i < N; i++) asm volatile("" : "+r"(d[i])::"memory");
}
__device__ __forceinline__ void conv_m1(const ConvC& K, uint32_t (&u)[16], uint32_t l) {
  wg_fence();
  wgmma_hrs_n64<1>(u, K.a1[0][0], K.a1[0][1], K.a1[0][2], K.a1[0][3], dsc(l, 32), 0);
  wgmma_hrs_n64<1>(u, K.a1[1][0], K.a1[1][1], K.a1[1][2], K.a1[1][3], dsc(l + 16, 32), 1);
  wg_commit();
}
__device__ __forceinline__ void conv_s2(const ConvC& K, uint32_t (&u)[16], uint32_t (&Z)[2][8], uint32_t dfl) {
  uint32_t fr[8], fi[8];
#pragma unroll
  for (int c = 0; c < 8; c++) {
    const uint32_t r = hfma(K.wa[c & 1], u[2 * c + 1], u[2 * c]);
    fi[c] = hfma(K.wb[c & 1], r, u[2 * c + 1]);
    fr[c] = hfma(K.wa[c & 1], fi[c], r);
  }
  wg_fence();
#pragma unroll
  for (int p = 0; p < 2; p++) {
    wgmma_hrs_n32<0>(Z[p], fr[4 * p], fr[4 * p + 2], fr[4 * p + 1], fr[4 * p + 3], dsc(dfl, 32), 0);
    wgmma_hrs_n32<0>(Z[p], fi[4 * p], fi[4 * p + 2], fi[4 * p + 1], fi[4 * p + 3], dsc(dfl + 16, 32), 1);
  }
  wg_commit();
}
__device__ __forceinline__ void conv_win(const ConvC& K, const uint32_t (&X)[2][8], uint32_t (&W)[2][8]) {
#pragma unroll
  for (int b = 0; b < 4; b++)
#pragma unroll
    for (int c = 0; c < 2; c++) {
      const uint32_t xr = X[b >> 1][2 * c + (b & 1)], xi = X[b >> 1][4 + 2 * c + (b & 1)];
      const int a = b ? b - 1 : 0;
      W[b >> 1][2 * c + (b & 1)] = b ? hfnma(K.sg, X[a >> 1][4 + 2 * c + (a & 1)], xr) : hmul16(xr, 0x3C003C00u);
      W[b >> 1][4 + 2 * c + (b & 1)] = b ? hfma(K.sg, X[a >> 1][2 * c + (a & 1)], xi) : hmul16(xi, 0x3C003C00u);
    }
}
template <int p>
__device__ __forceinline__ void conv_pw(uint32_t (&X)[2][8], uint32_t (&H)[2][8], uint32_t (&V)[8], uint32_t dil) {
  uint32_t pr[2][2], pi[2][2];
#pragma unroll
  for (int jj = 0; jj < 2; jj++)
#pragma unroll
    for (int c = 0; c < 2; c++) {
      const int j = 2 * p + jj;
      uint32_t sr = 0, si = 0;
#pragma unroll
      for (int a = 0; a <= j; a++) {
        const int b = j - a;
        const uint32_t hr = H[a >> 1][2 * c + (a & 1)], hi = H[a >> 1][4 + 2 * c + (a & 1)];
        const uint32_t xr = X[b >> 1][2 * c + (b & 1)], xi = X[b >> 1][4 + 2 * c + (b & 1)];
        sr = a == 0 ? hmul16(hr, xr) : hfma(hr, xr, sr);
        si = a == 0 ? hmul16(hr, xi) : hfma(hr, xi, si);
        sr = hfnma(hi, xi, sr);
        si = hfma(hi, xr, si);
      }
      pr[jj][c] = sr; pi[jj][c] = si;
    }
  wg_fence();
  wgmma_hrs_n32<0>(V, pr[0][0], pr[1][0], pr[0][1], pr[1][1], dsc(dil, 32), 0);
  wgmma_hrs_n32<0>(V, pi[0][0], pi[1][0], pi[0][1], pi[1][1], dsc(dil + 16, 32), 1);
  wg_commit();
}
template <int p>
__device__ __forceinline__ void conv_it(const ConvC& K, uint32_t (&V)[8], uint32_t vst) {
#pragma unroll
  for (int jj = 0; jj < 2; jj++) {
    uint32_t wr[2], wi[2];
#pragma unroll
    for (int c = 0; c < 2; c++) {
      const uint32_t r = hfnma(K.wa[c], V[4 + 2 * c + jj], V[2 * c + jj]);
      wi[c] = hfnma(K.wb[c], r, V[4 + 2 * c + jj]);
      wr[c] = hfnma(K.wa[c], wi[c], r);
    }
    stsm4(vst + (2 * p + jj) * 2048, wr[0], wr[1], wi[0], wi[1]);
  }
}
__device__ __forceinline__ void conv_m4(uint32_t (&y)[8], uint32_t (&a)[4][4], uint32_t d4l) {
  wg_fence();
  wgmma_hrs_n32<0>(y, a[0][0], a[0][1], a[0][2], a[0][3], dsc(d4l, 64), 0);
#pragma unroll
  for (int s = 1; s < 4; s++) wgmma_hrs_n32<0>(y, a[s][0], a[s][1], a[s][2], a[s][3], dsc(d4l + s * 16, 64), 1);
  wg_commit();
}

struct Params {
  CUtensorMap tmX, tmW, tmWo, tmK, tmV, tmQ, tmOA, tmOB;
  const __nv_bfloat16 *shift_k, *h, *D, *x, *w, *wo, *q;
  float *part, *kv;
  uint4* o;
  unsigned *ocnt, *epoch;
  const uint32_t *thr, *img;
};

__global__ void __cluster_dims__(2, 1, 1) __launch_bounds__(384, 1) fused_kernel(const __grid_constant__ Params P) {
  extern __shared__ __align__(1024) uint8_t smem[];
  const uint32_t sb = smem_u32(smem);
  const uint32_t bars = sb + OFF_BAR;
  const int tid = threadIdx.x, lane = tid & 31;
  const int warp = __shfl_sync(~0u, tid >> 5, 0);
  const int rank = blockIdx.x & 1, cl = blockIdx.x >> 1;
  const int mb = cl >> 3, hq = cl & 7;
  const int hp = 2 * hq + rank;
  const int rb = 2 * mb + (hq >> 2), cb = hq & 3;
#define BAR(i) (bars + 8 * (i))

  if (tid == 0) { STAMP(0, 0); GSTAMP(0, 30); }
  if (warp == 8) {
    if (elect_one()) {
      mbar_init(BAR(B_FULL1), 1);
      asm volatile("fence.mbarrier_init.release.cluster;" ::: "memory");
      mbar_expect(BAR(B_FULL1), STAGE_BYTES);
      tma3d(sb + 32768, &P.tmW, hp * 64, 0, 0, BAR(B_FULL1));
    }
    if (lane == 0) STAMP(3, 21);
  } else if (lane == 0) {
    const int wi = warp - (warp > 8);
#pragma unroll
    for (int r = 0; r < 6; r++)
      if (r < 5 || wi < B_COUNT - 56) mbar_init(BAR(1 + 11 * r + wi), ((uint32_t)(bar_counts(r) >> (4 * wi)) & 15) + 1);
    asm volatile("fence.mbarrier_init.release.cluster;" ::: "memory");
  }
  if (tid == 0) STAMP(2, 6);
  asm volatile("barrier.cluster.arrive.relaxed.aligned;\nbarrier.cluster.wait.aligned;" ::: "memory");
  if (warp == 8 && elect_one()) tma2d_mc(sb + rank * 16384, &P.tmX, 0, mb * 256 + rank * 128, BAR(B_FULL1));
  if (tid == 256) STAMP(2, 7);

  if (warp < 8) {
    asm volatile("setmaxnreg.inc.sync.aligned.u32 224;");
    const int wg = warp >> 2, w = warp & 3, g = lane >> 2, q = lane & 3, t = tid & 127;
    const bool elect = (t == 0);
    const uint32_t s16 = (sb & 0x3FFFF) >> 4;
    constexpr uint32_t SW128 = 64 | (1u << 30);
    uint32_t pq[2][16], v[32];
    ConvC K;
    {
      float acc[2][96];
      int st = 0, ph = 0;
#pragma unroll 1
      for (int kb = 0; kb < 16; kb++) {
        mbar_wait(BAR(B_FULL1 + st), ph);
        if (kb == 0 && elect) { STAMP(wg, 1); GSTAMP(wg, 26); }
        if (kb == 8 && elect) { STAMP(wg, 16); GSTAMP(wg, 25); }
        if (tid == 0) STAMP(2, 8 + kb);
        const uint32_t da = s16 + st * (STAGE_BYTES >> 4) + wg * 1024 + (1 << 16);
        const uint32_t db = s16 + st * (STAGE_BYTES >> 4) + 2048 + (512 << 16);
        if (kb == HOLD && wg == 0) asm volatile("bar.sync 3, 256;" ::: "memory");
        wg_fence();
#pragma unroll
        for (int ks = 0; ks < 4; ks++) {
          wgmma_ss_n192<0, 1>(acc[0], dsc(da + ks * 2, SW128), dsc(db + ks * 128, SW128), (kb | ks) != 0);
          wgmma_ss_n192<0, 1>(acc[1], dsc(da + 512 + ks * 2, SW128), dsc(db + ks * 128, SW128), (kb | ks) != 0);
        }
        wg_commit();
        wg_wait<1>();
        if (kb > 0 && t < 2) mbar_arrive_cl(BAR(B_EMPTY1 + (st == 0 ? 2 : st - 1)), t);
        if (++st == 3) { st = 0; ph ^= 1; }
      }
      if (HOLD < 16 && wg == 1) asm volatile("bar.arrive 3, 256;" ::: "memory");
      wg_wait<0>();
      keep(acc[0]); keep(acc[1]);
      if (t < 2) mbar_arrive_cl(BAR(B_EMPTY1 + 0), t);
      if (elect) { STAMP(wg, 2); GSTAMP(wg, 27); }
      mbar_wait(BAR(B_EMPTY1 + 2 - wg), 0);
      const uint32_t lrow = sb + (16 * w + 8 * ((lane >> 3) & 1) + (lane & 7)) * 128 + (((lane >> 4) ^ (lane & 7)) << 4);
      const uint32_t pko = OFF_H + wg * 8192, vo = OFF_VP - wg * 16384;
      if (elect) STAMP(wg, 18);
#pragma unroll
      for (int i = 0; i < 8; i += E1C)
        if (opaque_true()) {
#pragma unroll
          for (int j = i; j < i + E1C; j++) {
            const float* a = &acc[j >> 2][32 + 8 * (j & 3)];
            const float* b = a + 32;
            const uint32_t o = lrow ^ ((j & 3) * 32);
            stsm4(o + vo + (j >> 2) * 8192, pk2(b[0], b[1]), pk2(b[2], b[3]), pk2(b[4], b[5]), pk2(b[6], b[7]));
            stsm4(o + pko + (j >> 2) * 16384, phi2(a[0], a[1]), phi2(a[2], a[3]), phi2(a[4], a[5]), phi2(a[6], a[7]));
          }
          if (elect) STAMP(wg, 19 + i / 2);
        }
      fence_async();
      if (elect) STAMP(wg, 23);
      mbar_wait(BAR(B_XT), 0);
      bar_sync(1 + wg);
      if (elect) STAMP(wg, 3);
      float kva[36];
      wg_fence();
#pragma unroll
      for (int ks = 0; ks < 8; ks++) {
        const uint32_t vb = (vo >> 4) + ks * 128;
        wgmma_ss_n72<1, 1>(kva, dsc(s16 + (pko >> 4) + (ks >> 2) * 1024 + (ks & 3) * 128 + (1 << 16), SW128),
                           dsc(s16 + vb + (((OFF_ONES >> 4) - vb) << 16), SW128), ks != 0);
      }
      wg_commit();
      if (opaque_true()) {
#pragma unroll
        for (int i = 0; i < 16; i++) pq[0][i] = phi2(acc[0][2 * i], acc[0][2 * i + 1]);
      }
      wg_wait<0>();
      keep(kva);
      if (elect) STAMP(wg, 24);
      {
        float4 p[5];
#pragma unroll
        for (int c = 0; c < 4; c++)
          p[c] = w < 2 ? make_float4(kva[4 * c], kva[4 * c + 1], kva[4 * c + 2], kva[4 * c + 3])
                       : make_float4(kva[16 + 4 * c], kva[17 + 4 * c], kva[18 + 4 * c], kva[19 + 4 * c]);
        p[4] = make_float4(kva[32], kva[34], __shfl_down_sync(~0u, kva[32], 4), __shfl_down_sync(~0u, kva[34], 4));
        float4* hand = (float4*)(smem + OFF_VP - 16384) + t;
        if (wg == 1) {
          bar_sync(2);
#pragma unroll
          for (int c = 0; c < 5; c++) hand[c * 128] = p[c];
          asm volatile("bar.arrive 5, 256;" ::: "memory");
        } else {
          const uint32_t tag = ~*(volatile unsigned*)(smem + OFF_EPOCH) & 1;
          float* dst = P.part + (hp * 8 + mb) * 2176;
          asm volatile("bar.sync 5, 256;" ::: "memory");
#pragma unroll
          for (int c = 0; c < 5; c++) {
            const float4 u = hand[c * 128];
            if (c < 4 || !(lane & 7)) st_tag4(c < 4 ? dst + (c * 128 + t) * 4 : dst + 2048 + 16 * w + 2 * g, p[c].x + u.x, p[c].y + u.y, p[c].z + u.z, p[c].w + u.w, tag);
          }
          __syncwarp();
          if (lane == 0) mbar_arrive(BAR(B_PKFREE));
        }
      }
      if (elect) STAMP(wg, 4);
      {
        const uint4* ct = (const uint4*)P.thr + t;
        const uint4* hp4 = (const uint4*)(P.h + (blockIdx.x * 8 + warp) * 2048) + ((lane & 15) * 2 + (lane >> 4));
#pragma unroll
        for (int i = 0; i < 8; i++) { const uint4 u = __ldg(hp4 + i * 32); v[4 * i] = u.x; v[4 * i + 1] = u.y; v[4 * i + 2] = u.z; v[4 * i + 3] = u.w; }
#pragma unroll
        for (int s = 0; s < 2; s++) { const uint4 u = __ldg(ct + s * 128); K.a1[s][0] = u.x; K.a1[s][1] = u.y; K.a1[s][2] = u.z; K.a1[s][3] = u.w; }
        const uint4 u = __ldg(ct + 2 * 128);
        K.wa[0] = u.x; K.wa[1] = u.y; K.wb[0] = u.z; K.wb[1] = u.w;
        K.sg = (lane & 4) ? 0xBC00BC00u : 0x3C003C00u;
      }
      if (opaque_true()) {
#pragma unroll
        for (int i = 0; i < 16; i++) pq[1][i] = phi2(acc[1][2 * i], acc[1][2 * i + 1]);
      }
    }
    if (elect) STAMP(wg, 17);
    {
      const int e = normalise(v, lane == 0 ? *(const float*)(smem + OFF_D + 4 * warp) : 0.f);
      uint8_t* dst = smem + OFF_H + (w & 2) * 8192 + wg * 8192 + (w & 1) * 4096 + (lane >> 4) * 512 + (lane & 15) * 16;
#pragma unroll
      for (int i = 0; i < 8; i++)
        *(uint4*)(dst + (i >> 1) * 1024 + (i & 1) * 256) = make_uint4(v[4 * i], v[4 * i + 1], v[4 * i + 2], v[4 * i + 3]);
      if (lane < 2) st_async(mapa(sb + OFF_SCALE + (8 * rank + warp) * 4, lane), min(max(e + smem[OFF_EX + warp] - 124, 1), 254) << 23, mapa(BAR(B_Y), lane));
      fence_async();
      bar_sync(1 + wg);
    }
    if (elect) STAMP(wg, 5);
    {
      const uint32_t dfl = s16 + (OFF_F2F >> 4) + (8 << 16), dil = s16 + (OFF_F2I >> 4) + (8 << 16), d4l = s16 + (OFF_F4 >> 4) + (8 << 16);
      const uint32_t xl = s16 + (OFF_XT >> 4) + 4 * wg * (XT_STRIDE >> 4) + (8 << 16);
      const uint32_t hl = s16 + (OFF_H >> 4) + wg * 512 + (8 << 16);
      uint32_t vst = sb + wg * 8192 + w * 512 + lane * 16, vld = sb + wg * 8192 + w * 2048 + lane * 16;
      uint32_t ya = mapa(sb + OFF_XT + 4 * wg * XT_STRIDE + (2 * rank + (w & 1)) * 1024 + lane * 16, w >> 1);
      const uint32_t ybar = mapa(BAR(B_Y), w >> 1);
      asm volatile("" : "+r"(vst), "+r"(vld), "+r"(ya));
      uint32_t ux[16], uh[16], X[2][8], W[2][8], H[2][8], V0[8], V1[8], y[8], a[4][4];
#define YOUT(i) do { mbar_wait(BAR(B_XFREE + 4 * wg + (i)), 0); \
        st_async4(ya + (i) * XT_STRIDE, y[0], y[2], y[4], y[6], ybar); \
        st_async4(ya + (i) * XT_STRIDE + 512, y[1], y[3], y[5], y[7], ybar); } while (0)
      conv_m1(K, ux, xl);
      conv_m1(K, uh, hl);
      wg_wait<1>(); keepu(ux);
      if (lane == 0) mbar_arrive_cl(BAR(B_XFREE + 4 * wg), rank ^ 1);
      conv_s2(K, ux, X, dfl);
      wg_wait<1>(); keepu(uh);
      conv_s2(K, uh, H, dfl);
      wg_wait<1>(); keepu(X[0]); keepu(X[1]);
      conv_win(K, X, W);
      mbar_wait(BAR(B_PKFREE), 0);
      wg_wait<0>(); keepu(H[0]); keepu(H[1]);
#pragma unroll 1
      for (int i = 0; i < 3; i++) {
        if (i == (wg ? OC1 : OC0)) {
          if (elect) STAMP(wg, 8);
          mbar_wait(BAR(B_KV), 0);
          if (elect) STAMP(wg, 9);
          float oa[4][20];
          wg_fence();
#pragma unroll
          for (int m = 0; m < 8; m++) {
            const uint32_t* p = &pq[m >> 2][4 * (m & 3)];
            wgmma_rs_n40<1>(oa[m >> 1], p[0], p[1], p[2], p[3], dsc(s16 + (OFF_KVB >> 4) + ((m >> 1) & 1) * 160 + (m & 1) * 16 + (8 << 16), 32), m & 1);
          }
          wg_commit();
          uint4* ot = P.o + ((2 * mb + wg) * 16 + hp) * 1024 + (16 * w + g) * 8;
          wg_wait<0>();
#pragma unroll
          for (int m = 0; m < 4; m++) {
            float (&o)[20] = oa[m];
            keep(o);
            const uint32_t den = hadd(pk2(o[16], o[18]), 0x35863586u);
#pragma unroll
            for (int r = 0; r < 2; r++) {
              const float ri = rcp_fast(__uint_as_float(r ? (den & 0xFFFF0000u) : (den << 16)));
              uint4 u;
              u.x = pk2(o[2 * r] * ri, o[2 * r + 1] * ri);
              u.y = pk2(o[4 + 2 * r] * ri, o[5 + 2 * r] * ri);
              u.z = pk2(o[8 + 2 * r] * ri, o[9 + 2 * r] * ri);
              u.w = pk2(o[12 + 2 * r] * ri, o[13 + 2 * r] * ri);
              __stcg(ot + (64 * (m >> 1) + 8 * r) * 8 + ((4 * (m & 1) + q) ^ g), u);
            }
          }
          __syncwarp();
          if (lane == 0) mbar_arrive(BAR(B_ODONE));
          if (elect) STAMP(wg, 10);
        }
        const int n = i + 1;
        const uint32_t vo = (i & 1) ? OFF_H : OFF_VP;
        conv_m1(K, ux, xl + n * (XT_STRIDE >> 4));
        conv_m1(K, uh, hl + (n >> 1) * 1024 + (n & 1) * 256);
        conv_pw<0>(W, H, V0, dil);
        conv_pw<1>(W, H, V1, dil);
        wg_wait<2>(); keepu(ux); keepu(uh);
        if (lane == 0) mbar_arrive_cl(BAR(B_XFREE + 4 * wg + n), rank ^ 1);
        conv_s2(K, ux, X, dfl);
        wg_wait<1>(); keepu(V0); keepu(V1);
        conv_it<0>(K, V0, vst + vo);
        conv_it<1>(K, V1, vst + vo);
        bar_sync(1 + wg);
#pragma unroll
        for (int s = 0; s < 4; s++) ldsm4t(a[s], vld + vo + s * 512);
        conv_s2(K, uh, H, dfl);
        conv_m4(y, a, d4l);
        if (i > 0 && lane < 2) mbar_arrive_cl(BAR(B_AFREE + i - 1), lane);
        wg_wait<2>(); keepu(X[0]); keepu(X[1]);
        conv_win(K, X, W);
        wg_wait<0>(); keepu(H[0]); keepu(H[1]); keepu(y);
        YOUT(i);
        if (elect) STAMP(wg, i < 2 ? 6 + i : 9 + i);
      }
      conv_pw<0>(W, H, V0, dil);
      conv_pw<1>(W, H, V1, dil);
      wg_wait<1>(); keepu(V0);
      conv_it<0>(K, V0, vst + OFF_H + 16384);
      wg_wait<0>(); keepu(V1);
      conv_it<1>(K, V1, vst + OFF_H + 16384);
      bar_sync(1 + wg);
#pragma unroll
      for (int s = 0; s < 4; s++) ldsm4t(a[s], vld + OFF_H + 16384 + s * 512);
      conv_m4(y, a, d4l);
      if (lane < 2) mbar_arrive_cl(BAR(B_AFREE + 2), lane);
      wg_wait<0>(); keepu(y);
      YOUT(3);
      if (lane == 0) mbar_arrive(BAR(B_Y));
      if (elect) STAMP(wg, 12);
    }
    {
      float acc[64];
#pragma unroll 1
      for (int kb = 0; kb < 16; kb++) {
        mbar_wait(BAR(B_FULL2 + kb), 0);
        if (kb == 0 && elect) { STAMP(wg, 13); GSTAMP(wg, 28); }
        const uint32_t da = s16 + ((uint32_t)(SLOT_A >> (4 * kb)) & 15) * 1024 + wg * 512 + (1 << 16);
        const uint32_t db = s16 + ((uint32_t)(SLOT_B >> (4 * kb)) & 15) * 1024 + (512 << 16);
        wg_fence();
#pragma unroll
        for (int ks = 0; ks < 4; ks++) wgmma_ss_n128<0, 1>(acc, dsc(da + ks * 2, SW128), dsc(db + ks * 128, SW128), (kb | ks) != 0);
        wg_commit();
        wg_wait<1>();
        if (kb > 0 && kb < 14 && t < 2 && (kb <= 11 || t == rank)) mbar_arrive_cl(BAR(B_CONS2 + kb - 1), t);
      }
      wg_wait<0>();
      keep(acc);
      if (elect) { STAMP(wg, 14); GSTAMP(wg, 29); }
      mbar_wait(BAR(B_CONS2 + 12), 0);
      const uint32_t stg = sb + (wg ? 5 : 2) * 16384;
      const uint32_t lrow = stg + (16 * w + 8 * ((lane >> 3) & 1) + (lane & 7)) * 128 + (((lane >> 4) ^ (lane & 7)) << 4);
#pragma unroll
      for (int cp = 0; cp < 8; cp++) {
        const float* a = &acc[8 * cp];
        stsm4((lrow ^ ((cp & 3) * 32)) + (cp >> 2) * 8192, pk2(a[0], a[1]), pk2(a[2], a[3]), pk2(a[4], a[5]), pk2(a[6], a[7]));
      }
      fence_async();
      bar_sync(1 + wg);
      if (elect) {
        const int col = 1024 + 256 * cb + 128 * rank, row = 128 * rb + 64 * wg;
        tma2d_st(&P.tmOB, stg, col, row);
        tma2d_st(&P.tmOB, stg + 8192, col + 64, row);
        asm volatile("cp.async.bulk.commit_group;\ncp.async.bulk.wait_group.read 0;" ::: "memory");
        STAMP(wg, 15); GSTAMP(wg, 31); PDUMP(wg);
      }
    }
  } else {
    asm volatile("setmaxnreg.dec.sync.aligned.u32 56;");
    if (warp == 8) {
      if (lane == 0) STAMP(3, 20);
      int st = 1, ph = 1;
      const uint8_t* pfx = (const uint8_t*)P.x + (mb * 256 + hp * 16 + (lane & 15)) * 2048;
      const uint8_t* pfw = (const uint8_t*)P.w + (mb * 8 + (lane & 7)) * 6144 + (lane >> 3) * 2048 + hp * 128;
#pragma unroll 1
      for (int kb = 1; kb < 16; kb++) {
        if (kb >= 3) mbar_wait(BAR(B_EMPTY1 + st), ph);
        const uint32_t sa = sb + st * STAGE_BYTES;
        if (elect_one()) {
          mbar_expect(BAR(B_FULL1 + st), STAGE_BYTES);
          tma2d_mc(sa + rank * 16384, &P.tmX, kb * 64, mb * 256 + rank * 128, BAR(B_FULL1 + st));
          tma3d(sa + 32768, &P.tmW, hp * 64, kb * 64, 0, BAR(B_FULL1 + st));
        }
        if (kb == 1 && lane == 0) STAMP(2, 24);
        if (PFD && kb >= 2) {
#pragma unroll 1
          for (int j = kb == 2 ? 3 : kb + PFD; j <= kb + PFD && j < 16; j++) {
            if (lane < 16) asm volatile("prefetch.global.L2 [%0];" ::"l"(pfx + j * 128));
            if (lane < 24) asm volatile("prefetch.global.L2 [%0];" ::"l"(pfw + j * (64 * 6144)));
          }
          if (kb >= QPF && kb < QPF + 8) asm volatile("prefetch.global.L2 [%0];" ::"l"((const uint8_t*)P.q + (blockIdx.x * 256 + (kb - QPF) * 32 + lane) * 128));
          if (kb >= 4)
            asm volatile("prefetch.global.L2 [%0];" ::"l"(kb < 12 ? (const uint8_t*)P.h + (blockIdx.x * 256 + (kb - 4) * 32 + lane) * 128
                                                                  : (const uint8_t*)P.wo + (blockIdx.x * 128 + (kb - 12) * 32 + lane) * 128));
        }
        if (++st == 3) { st = 0; ph ^= 1; }
      }
      if (lane == 0) STAMP(2, 1);
      const unsigned epoch = P.epoch[blockIdx.x];
#define SLOT(tab, kb) (sb + ((uint32_t)((tab) >> (4 * (kb))) & 15) * 16384)
#define LOAD_B(kb) tma3d(SLOT(SLOT_B, kb), &P.tmWo, 0, (kb) * 64, 4 * cb + 2 * rank, BAR(B_FULL2 + (kb)))
#define LOAD_A(kb) bulk_ld_mc(SLOT(SLOT_A, kb) + rank * 8192, P.o + (rb * 16 + (kb)) * 1024 + rank * 512, 8192, BAR(B_FULL2 + (kb)))
      mbar_wait(BAR(B_EMPTY1 + 1), 0);
#pragma unroll 1
      for (int kb = 0; kb < 7; kb++) {
        if (kb == 1) mbar_wait(BAR(B_EMPTY1 + 2), 0);
        if (kb == 2) mbar_wait(BAR(B_EMPTY1 + 0), 1);
        if (kb == 6) mbar_wait(BAR(BPRE), 0);
        if (elect_one()) {
          mbar_expect(BAR(B_FULL2 + kb), 16384);
          LOAD_B(kb);
          if (kb == 1) {
            mbar_expect(BAR(B_Q), 8192);
#pragma unroll 1
            for (int ci = 6; ci < 10; ci++) tma3d(sb + OFF_SPARE + 2048 * (ci - 6), &P.tmQ, 16 * cl, 64 * rank + 32 * (ci >> 3), 2 * (ci & 7), BAR(B_Q));
          }
        }
      }
      if (lane == 0) STAMP(2, 2);
      poll_ge(&P.ocnt[rb * 32], 16 * (epoch + 1));
      asm volatile("fence.proxy.async.global;" ::: "memory");
      if (lane == 0) STAMP(2, 3);
#pragma unroll 1
      for (int kb = 0; kb < 7; kb++) {
        mbar_wait(BAR(kb < 3 ? B_AFREE + kb : B_CONS2 + ((kb - 3) >> 1)), 0);
        if (elect_one()) {
          mbar_expect(BAR(B_FULL2 + kb), 16384);
          LOAD_A(kb);
        }
        if (kb == 2 && lane == 0) STAMP(2, 4);
      }
#pragma unroll 1
      for (int kb = 7; kb < 16; kb++) {
        mbar_wait(BAR(B_CONS2 + kb - 5), 0);
        if (elect_one()) { mbar_expect(BAR(B_FULL2 + kb), 32768); LOAD_A(kb); LOAD_B(kb); }
      }
      if (lane == 0) { P.epoch[blockIdx.x] = epoch + 1; STAMP(2, 5); PDUMP(2); }
    } else {
      const uint32_t clk0 = clock();
      const int hw = warp - 9, g = lane >> 2, q = lane & 3;
      const unsigned epoch = P.epoch[blockIdx.x];
      const uint32_t tag = ~epoch & 1;
      const uint32_t stg = sb + OFF_STG + hw * STG_STRIDE, sbar = BAR(B_STG + 2 * hw);
      int ph = 0;
      {
        uint32_t tap[2][4];
#pragma unroll
        for (int cg = 0; cg < 2; cg++) {
          const uint2 u = __ldg((const uint2*)(P.shift_k + (16 * cl + 8 * cg + g) * 4));
          tap[cg][0] = __byte_perm(u.x, 0, 0x1010); tap[cg][1] = __byte_perm(u.x, 0, 0x3232);
          tap[cg][2] = __byte_perm(u.y, 0, 0x1010); tap[cg][3] = __byte_perm(u.y, 0, 0x3232);
        }
        if (hw == 0 && lane < 8) *(float*)(smem + OFF_D + 4 * lane) = __bfloat162float(P.D[blockIdx.x * 8 + lane]);
        if (hw == 1) asm volatile("prefetch.global.L2 [%0];" ::"l"(P.thr + (lane + 32 * (blockIdx.x & 1)) * 32));
        if (hw == 0 && elect_one()) {
          *(volatile unsigned*)(smem + OFF_EPOCH) = epoch;
          mbar_expect(BAR(B_XRAW), 32768);
          mbar_expect(BAR(B_Y), 32768 + 64);
        }
        if (lane == 0) STAMP(3, hw);
        const uint32_t xo = sb + OFF_XT + g * XT_STRIDE + rank * 2048 + q * 4;
        const int krow = 8 + (lane & 7) - (lane >> 3);
        const uint32_t ka = stg + krow * 32 + ((krow & 4) << 2), va = stg + 2304 + lane * 32 + ((lane & 4) << 2);
        int b = 0;
#pragma unroll 1
        for (int ci = hw - 3; ci < 16; ci += 3) {
          const uint32_t bo = b ? OFF_F2F - OFF_STG : 0, bn = b ? 0 : OFF_F2F - OFF_STG;
          if (ci + 3 < 16) {
            while ((uint32_t)clock() - clk0 < HSTART + (ci + 3) * PACE) __nanosleep(64);
            if (elect_one()) {
              mbar_expect(sbar + 8 * (b ^ 1), 2304 + 2048);
              tma2d(stg + bn, &P.tmK, 16 * cl, 1024 * rank + 64 * (ci + 3) - 8, sbar + 8 * (b ^ 1));
              tma2d(stg + bn + 2304, &P.tmV, 16 * cl, 1024 * rank + 64 * (ci + 3), sbar + 8 * (b ^ 1));
            }
          }
          if (ci >= 0) {
            mbar_wait(sbar + 8 * b, (ph >> b) & 1);
            ph ^= 1 << b;
#pragma unroll 1
            for (int grp = 0; grp < 2; grp++) {
#pragma unroll
              for (int cg = 0; cg < 2; cg++) {
                const uint32_t dst = mapa(xo + (ci >> 3) * 1024 + ((ci & 7) * 4 + 2 * grp) * 16, cg), xbar = mapa(BAR(B_XRAW), cg);
                uint32_t vv[4], kk[4][4];
                ldsm4t(vv, (va ^ (cg * 16)) + bo + grp * 1024);
#pragma unroll
                for (int rg = 0; rg < 4; rg++) ldsm4t(kk[rg], (ka ^ (cg * 16)) + bo + grp * 1024 + rg * 256);
#pragma unroll
                for (int rg = 0; rg < 4; rg++)
                  vv[rg] = hmul(hadd(hadd(hadd(hmul(kk[rg][3], tap[cg][3]), hmul(kk[rg][2], tap[cg][2])), hmul(kk[rg][1], tap[cg][1])), hmul(kk[rg][0], tap[cg][0])), vv[rg]);
#pragma unroll
                for (int rg = 0; rg < 4; rg++) st_async(dst + (rg & 1) * 512 + (rg >> 1) * 16, vv[rg], xbar);
              }
            }
          }
          b ^= 1;
        }
      }
      if (lane == 0) STAMP(3, 3 + hw);
      asm volatile("bar.sync 4, 96;" ::: "memory");
      if (hw == 0 && elect_one()) { mbar_expect(BAR(B_XT), 10240); bulk_ld(sb + OFF_F2F, P.img, 10240, BAR(B_XT)); }
      mbar_wait(BAR(B_XRAW), 0);
#pragma unroll 1
      for (int c = hw; c < 8; c += 3) {
        uint4* p = (uint4*)(smem + OFF_XT + c * XT_STRIDE) + lane;
        uint32_t v[32];
#pragma unroll
        for (int i = 0; i < 8; i++) { const uint4 u = p[i * 32]; v[4 * i] = u.x; v[4 * i + 1] = u.y; v[4 * i + 2] = u.z; v[4 * i + 3] = u.w; }
        const int e = normalise(v, 0.f);
#pragma unroll
        for (int i = 0; i < 8; i++) p[i * 32] = make_uint4(v[4 * i], v[4 * i + 1], v[4 * i + 2], v[4 * i + 3]);
        if (lane == 0) smem[OFF_EX + c] = e;
        if (c < 6 && elect_one()) {
          if (c < 3) mbar_expect(sbar, 4096);
          tma3d(sb + OFF_STG + 2048 * c, &P.tmQ, 16 * cl, 64 * rank, 2 * c, sbar);
        }
      }
      fence_async();
      __syncwarp();
      if (lane == 0) { mbar_arrive(BAR(B_XT)); STAMP(3, 13 + hw); }
      mbar_wait(BAR(B_PKFREE), 0);
      if (hw == 0 && lane == 0) STAMP(3, 19);
      if (PD1) __nanosleep(PD1);
      {
        const int pi = hw < 2 ? 64 * mb + 32 * hw + lane : 512 + 2 * mb + (lane & 1);
        const float* psrc = P.part + hp * 8 * 2176 + 4 * pi;
        uint4 f[8];
        int n = 0;
        uint32_t bad;
        do {
#pragma unroll
          for (int p = 0; p < 8; p++) f[p] = ld_rlx4(psrc + p * 2176);
          bad = stale8(f, tag);
          if (++n > SPIN_LIMIT) __trap();
        } while (__any_sync(~0u, bad & 1));
        float s0 = 0.f, s1 = 0.f, s2 = 0.f, s3 = 0.f;
#pragma unroll
        for (int p = 0; p < 8; p++) { s0 += __uint_as_float(f[p].x); s1 += __uint_as_float(f[p].y); s2 += __uint_as_float(f[p].z); s3 += __uint_as_float(f[p].w); }
        if (hw < 2 || lane < 2) st_tag4(P.kv + hp * 2176 + (4 * pi), s0, s1, s2, s3, tag);
      }
      if (lane == 0 && hw == 0) STAMP(3, 8);
      if (hw == 2) {
        mbar_wait(BAR(B_ODONE), 0);
        if (lane < 2) {
          asm volatile("red.release.gpu.global.add.u32 [%0], 1;" ::"l"(&P.ocnt[(2 * mb + lane) * 32]) : "memory");
        }
        if (lane == 0) STAMP(3, 7);
        __syncwarp();
      } else {
        if (PD2) __nanosleep(PD2);
        const int t = hw * 32 + lane;
        uint4 f[8];
        const float* src = P.kv + hp * 2176 + (4 * t);
        const float* zsrc = P.kv + hp * 2176 + (2048 + (t & 48) + 2 * (lane & 6));
        uint4 zp;
        uint32_t bad;
        int n = 0;
        do {
          zp = ld_rlx4(zsrc);
#pragma unroll
          for (int p = 0; p < 8; p++) f[p] = ld_rlx4(src + 4 * ((p & 3) * 128 + (p >> 2) * 64));
          bad = stale8(f, tag) | (zp.x ^ tag);
          if (++n > SPIN_LIMIT) __trap();
        } while (__any_sync(~0u, bad & 1));
#define PK2U(a, b) pk2(__uint_as_float(a), __uint_as_float(b))
#pragma unroll
        for (int hh = 0; hh < 2; hh++) {
          const uint4* ff = &f[4 * hh];
          uint8_t* dst = smem + OFF_KVB + hh * 2560 + q * 512 + (16 * hw + g) * 16;
          *(uint4*)dst = make_uint4(PK2U(ff[0].x, ff[0].y), PK2U(ff[1].x, ff[1].y), PK2U(ff[2].x, ff[2].y), PK2U(ff[3].x, ff[3].y));
          *(uint4*)(dst + 128) = make_uint4(PK2U(ff[0].z, ff[0].w), PK2U(ff[1].z, ff[1].w), PK2U(ff[2].z, ff[2].w), PK2U(ff[3].z, ff[3].w));
        }
        const uint32_t zf = (lane & 1) ? ((lane & 8) ? zp.w : zp.z) : ((lane & 8) ? zp.y : zp.x);
        const uint32_t zz = PK2U(zf, zf);
        *(uint4*)(smem + OFF_KVB + hw * 2560 + 2048 + lane * 16) = make_uint4(zz, zz, zz, zz);
        fence_async();
        __syncwarp();
        if (lane == 0) { mbar_arrive(BAR(B_KV)); if (hw == 0) STAMP(3, 9); }
      }
#define QBUF(ci) (sb + 2048 * (ci) + ((ci) < 6 ? OFF_STG : (ci) < 10 ? OFF_SPARE - 6 * 2048 : OFF_F2F - 10 * 2048))
      mbar_wait(BAR(B_Y), 0);
      if (elect_one()) {
        mbar_expect(sbar + 8, 4096);
#pragma unroll 1
        for (int ci = hw ? hw + 9 : 12; ci < 16; ci += 3) tma3d(QBUF(ci), &P.tmQ, 16 * cl, 64 * rank + 32, 2 * (ci & 7), sbar + 8);
      }
      mbar_wait(BAR(B_Q), 0);
      {
        const float2 sc0 = *(const float2*)(smem + OFF_SCALE + 8 * q), sc1 = *(const float2*)(smem + OFF_SCALE + 32 + 8 * q);
        const uint32_t yl = sb + OFF_XT + (lane & 7) * XT_STRIDE + (lane >> 3) * 16;
#pragma unroll 1
        for (int ci = hw; ci < 16; ci += 3) {
          const uint32_t qb = QBUF(ci);
          const int b = ci >= 10;
          mbar_wait(sbar + 8 * b, (ph >> b) & 1);
#pragma unroll 1
          for (int nl = 0; nl < 2; nl++) {
            uint32_t yy[2][4], qq[2][4];
            const uint32_t qa = qb + lane * 32 + ((lane & 4) << 2) + nl * 1024;
#pragma unroll
            for (int cg = 0; cg < 2; cg++) { ldsm4t(yy[cg], yl + cg * 2048 + (2 * ci + nl) * 64); ldsm4(qq[cg], qa ^ (cg * 16)); }
#pragma unroll
            for (int cg = 0; cg < 2; cg++) {
              const float2 sc = cg ? sc1 : sc0;
#pragma unroll
              for (int m = 0; m < 4; m++) {
                const float2 f = __half22float2(*(const __half2*)&yy[cg][m]);
                qq[cg][m] = hmul(qq[cg][m], pk2(f.x * sc.x, f.y * sc.y));
              }
              stsm4(qa ^ (cg * 16), qq[cg][0], qq[cg][1], qq[cg][2], qq[cg][3]);
            }
          }
          fence_async();
          __syncwarp();
          if (elect_one()) tma3d_st(&P.tmOA, qb, 16 * cl, 64 * rank + 32 * (ci >> 3), 2 * (ci & 7));
        }
        asm volatile("cp.async.bulk.commit_group;\ncp.async.bulk.wait_group.read 0;" ::: "memory");
      }
      if (lane == 0) STAMP(3, 10 + hw);
    }
  }
}

typedef CUresult (*EncodeFn)(CUtensorMap*, CUtensorMapDataType, cuuint32_t, void*, const cuuint64_t*, const cuuint64_t*,
                             const cuuint32_t*, const cuuint32_t*, CUtensorMapInterleave, CUtensorMapSwizzle,
                             CUtensorMapL2promotion, CUtensorMapFloatOOBfill);

static void enc(EncodeFn fn, CUtensorMap* m, const void* p, int rank, const cuuint64_t* dims, const cuuint64_t* strides,
                const cuuint32_t* box, CUtensorMapSwizzle swz, CUtensorMapL2promotion promo) {
  cuuint32_t es[3] = {1, 1, 1};
  fn(m, CU_TENSOR_MAP_DATA_TYPE_BFLOAT16, rank, (void*)p, dims, strides, box, es, CU_TENSOR_MAP_INTERLEAVE_NONE, swz, promo,
     CU_TENSOR_MAP_FLOAT_OOB_FILL_NONE);
}

extern "C" void kernel_launch(void* const* d_in, const int* in_sizes, int n_in, void* d_out, int out_size) {
  void* fp = nullptr;
  cudaDriverEntryPointQueryResult qr;
  cudaGetDriverEntryPoint("cuTensorMapEncodeTiled", &fp, cudaEnableDefault, &qr);
  EncodeFn fn = (EncodeFn)fp;
  Params P;
  P.shift_k = (const __nv_bfloat16*)d_in[3]; P.h = (const __nv_bfloat16*)d_in[4]; P.D = (const __nv_bfloat16*)d_in[5];
  P.q = (const __nv_bfloat16*)d_in[0];
  cudaGetSymbolAddress((void**)&P.part, g_part); cudaGetSymbolAddress((void**)&P.kv, g_kv); cudaGetSymbolAddress((void**)&P.o, g_o);
  cudaGetSymbolAddress((void**)&P.ocnt, g_ocnt); cudaGetSymbolAddress((void**)&P.epoch, g_epoch);
  cudaGetSymbolAddress((void**)&P.thr, c_thr); cudaGetSymbolAddress((void**)&P.img, c_img);
  P.x = (const __nv_bfloat16*)d_in[6]; P.w = (const __nv_bfloat16*)d_in[7]; P.wo = (const __nv_bfloat16*)d_in[8];
  const CUtensorMapSwizzle S128 = CU_TENSOR_MAP_SWIZZLE_128B, S32 = CU_TENSOR_MAP_SWIZZLE_32B;
  const CUtensorMapL2promotion P0 = CU_TENSOR_MAP_L2_PROMOTION_NONE, P128 = CU_TENSOR_MAP_L2_PROMOTION_L2_128B;
  { cuuint64_t d[2] = {1024, 2048}, s[1] = {2048}; cuuint32_t b[2] = {64, 128}; enc(fn, &P.tmX, d_in[6], 2, d, s, b, S128, P128); }
  { cuuint64_t d[3] = {1024, 1024, 3}, s[2] = {6144, 2048}; cuuint32_t b[3] = {64, 64, 3}; enc(fn, &P.tmW, d_in[7], 3, d, s, b, S128, P128); }
  { cuuint64_t d[3] = {64, 1024, 16}, s[2] = {2048, 128}; cuuint32_t b[3] = {64, 64, 2}; enc(fn, &P.tmWo, d_in[8], 3, d, s, b, S128, P128); }
  { cuuint64_t d[2] = {1024, 2048}, s[1] = {2048}; cuuint32_t b[2] = {16, 72}; enc(fn, &P.tmK, d_in[1], 2, d, s, b, S32, PKV); }
  { cuuint64_t d[2] = {1024, 2048}, s[1] = {2048}; cuuint32_t b[2] = {16, 64}; enc(fn, &P.tmV, d_in[2], 2, d, s, b, S32, PKV); }
  { cuuint64_t d[3] = {1024, 128, 16}, s[2] = {32768, 2048}; cuuint32_t b[3] = {16, 32, 2}; enc(fn, &P.tmQ, d_in[0], 3, d, s, b, S32, PKV); }
  { cuuint64_t d[3] = {1024, 128, 16}, s[2] = {65536, 4096}; cuuint32_t b[3] = {16, 32, 2}; enc(fn, &P.tmOA, d_out, 3, d, s, b, S32, P0); }
  { cuuint64_t d[2] = {2048, 2048}, s[1] = {4096}; cuuint32_t b[2] = {64, 64}; enc(fn, &P.tmOB, d_out, 2, d, s, b, S128, P0); }
  cudaFuncSetAttribute(fused_kernel, cudaFuncAttributeMaxDynamicSharedMemorySize, SMEM_TOTAL);
  fused_kernel<<<128, 384, SMEM_TOTAL>>>(P);
}
```

```cpp
#include <cuda_runtime.h>
#include <cuda_bf16.h>
#include <cuda_fp16.h>
#include <cuda.h>
#include <stdint.h>

template<int TA, int TB, int SA=1> __device__ __forceinline__ void wgmma_ss_n192(float (&d)[96], uint64_t da, uint64_t db, int scale_d) {
  asm volatile("{\n.reg .pred p;\nsetp.ne.b32 p, %98, 0;\n"
    "wgmma.mma_async.sync.aligned.m64n192k16.f32.bf16.bf16 {%0, %1, %2, %3, %4, %5, %6, %7, %8, %9, %10, %11, %12, %13, %14, %15, %16, %17, %18, %19, %20, %21, %22, %23, %24, %25, %26, %27, %28, %29, %30, %31, %32, %33, %34, %35, %36, %37, %38, %39, %40, %41, %42, %43, %44, %45, %46, %47, %48, %49, %50, %51, %52, %53, %54, %55, %56, %57, %58, %59, %60, %61, %62, %63, %64, %65, %66, %67, %68, %69, %70, %71, %72, %73, %74, %75, %76, %77, %78, %79, %80, %81, %82, %83, %84, %85, %86, %87, %88, %89, %90, %91, %92, %93, %94, %95}, %96, %97, p, %101, 1, %99, %100;\n}\n"
    : "+f"(d[0]), "+f"(d[1]), "+f"(d[2]), "+f"(d[3]), "+f"(d[4]), "+f"(d[5]), "+f"(d[6]), "+f"(d[7]), "+f"(d[8]), "+f"(d[9]), "+f"(d[10]), "+f"(d[11]), "+f"(d[12]), "+f"(d[13]), "+f"(d[14]), "+f"(d[15]), "+f"(d[16]), "+f"(d[17]), "+f"(d[18]), "+f"(d[19]), "+f"(d[20]), "+f"(d[21]), "+f"(d[22]), "+f"(d[23]), "+f"(d[24]), "+f"(d[25]), "+f"(d[26]), "+f"(d[27]), "+f"(d[28]), "+f"(d[29]), "+f"(d[30]), "+f"(d[31]), "+f"(d[32]), "+f"(d[33]), "+f"(d[34]), "+f"(d[35]), "+f"(d[36]), "+f"(d[37]), "+f"(d[38]), "+f"(d[39]), "+f"(d[40]), "+f"(d[41]), "+f"(d[42]), "+f"(d[43]), "+f"(d[44]), "+f"(d[45]), "+f"(d[46]), "+f"(d[47]), "+f"(d[48]), "+f"(d[49]), "+f"(d[50]), "+f"(d[51]), "+f"(d[52]), "+f"(d[53]), "+f"(d[54]), "+f"(d[55]), "+f"(d[56]), "+f"(d[57]), "+f"(d[58]), "+f"(d[59]), "+f"(d[60]), "+f"(d[61]), "+f"(d[62]), "+f"(d[63]), "+f"(d[64]), "+f"(d[65]), "+f"(d[66]), "+f"(d[67]), "+f"(d[68]), "+f"(d[69]), "+f"(d[70]), "+f"(d[71]), "+f"(d[72]), "+f"(d[73]), "+f"(d[74]), "+f"(d[75]), "+f"(d[76]), "+f"(d[77]), "+f"(d[78]), "+f"(d[79]), "+f"(d[80]), "+f"(d[81]), "+f"(d[82]), "+f"(d[83]), "+f"(d[84]), "+f"(d[85]), "+f"(d[86]), "+f"(d[87]), "+f"(d[88]), "+f"(d[89]), "+f"(d[90]), "+f"(d[91]), "+f"(d[92]), "+f"(d[93]), "+f"(d[94]), "+f"(d[95])
    : "l"(da), "l"(db), "r"(scale_d), "n"(TA), "n"(TB), "n"(SA));
}
template<int TA, int TB, int SA=1> __device__ __forceinline__ void wgmma_ss_n128(float (&d)[64], uint64_t da, uint64_t db, int scale_d) {
  asm volatile("{\n.reg .pred p;\nsetp.ne.b32 p, %66, 0;\n"
    "wgmma.mma_async.sync.aligned.m64n128k16.f32.bf16.bf16 {%0, %1, %2, %3, %4, %5, %6, %7, %8, %9, %10, %11, %12, %13, %14, %15, %16, %17, %18, %19, %20, %21, %22, %23, %24, %25, %26, %27, %28, %29, %30, %31, %32, %33, %34, %35, %36, %37, %38, %39, %40, %41, %42, %43, %44, %45, %46, %47, %48, %49, %50, %51, %52, %53, %54, %55, %56, %57, %58, %59, %60, %61, %62, %63}, %64, %65, p, %69, 1, %67, %68;\n}\n"
    : "+f"(d[0]), "+f"(d[1]), "+f"(d[2]), "+f"(d[3]), "+f"(d[4]), "+f"(d[5]), "+f"(d[6]), "+f"(d[7]), "+f"(d[8]), "+f"(d[9]), "+f"(d[10]), "+f"(d[11]), "+f"(d[12]), "+f"(d[13]), "+f"(d[14]), "+f"(d[15]), "+f"(d[16]), "+f"(d[17]), "+f"(d[18]), "+f"(d[19]), "+f"(d[20]), "+f"(d[21]), "+f"(d[22]), "+f"(d[23]), "+f"(d[24]), "+f"(d[25]), "+f"(d[26]), "+f"(d[27]), "+f"(d[28]), "+f"(d[29]), "+f"(d[30]), "+f"(d[31]), "+f"(d[32]), "+f"(d[33]), "+f"(d[34]), "+f"(d[35]), "+f"(d[36]), "+f"(d[37]), "+f"(d[38]), "+f"(d[39]), "+f"(d[40]), "+f"(d[41]), "+f"(d[42]), "+f"(d[43]), "+f"(d[44]), "+f"(d[45]), "+f"(d[46]), "+f"(d[47]), "+f"(d[48]), "+f"(d[49]), "+f"(d[50]), "+f"(d[51]), "+f"(d[52]), "+f"(d[53]), "+f"(d[54]), "+f"(d[55]), "+f"(d[56]), "+f"(d[57]), "+f"(d[58]), "+f"(d[59]), "+f"(d[60]), "+f"(d[61]), "+f"(d[62]), "+f"(d[63])
    : "l"(da), "l"(db), "r"(scale_d), "n"(TA), "n"(TB), "n"(SA));
}
template<int TA, int TB, int SA=1> __device__ __forceinline__ void wgmma_ss_n72(float (&d)[36], uint64_t da, uint64_t db, int scale_d) {
  asm volatile("{\n.reg .pred p;\nsetp.ne.b32 p, %38, 0;\n"
    "wgmma.mma_async.sync.aligned.m64n72k16.f32.bf16.bf16 {%0, %1, %2, %3, %4, %5, %6, %7, %8, %9, %10, %11, %12, %13, %14, %15, %16, %17, %18, %19, %20, %21, %22, %23, %24, %25, %26, %27, %28, %29, %30, %31, %32, %33, %34, %35}, %36, %37, p, %41, 1, %39, %40;\n}\n"
    : "+f"(d[0]), "+f"(d[1]), "+f"(d[2]), "+f"(d[3]), "+f"(d[4]), "+f"(d[5]), "+f"(d[6]), "+f"(d[7]), "+f"(d[8]), "+f"(d[9]), "+f"(d[10]), "+f"(d[11]), "+f"(d[12]), "+f"(d[13]), "+f"(d[14]), "+f"(d[15]), "+f"(d[16]), "+f"(d[17]), "+f"(d[18]), "+f"(d[19]), "+f"(d[20]), "+f"(d[21]), "+f"(d[22]), "+f"(d[23]), "+f"(d[24]), "+f"(d[25]), "+f"(d[26]), "+f"(d[27]), "+f"(d[28]), "+f"(d[29]), "+f"(d[30]), "+f"(d[31]), "+f"(d[32]), "+f"(d[33]), "+f"(d[34]), "+f"(d[35])
    : "l"(da), "l"(db), "r"(scale_d), "n"(TA), "n"(TB), "n"(SA));
}
template<int TB, int SA=1> __device__ __forceinline__ void wgmma_rs_n40(float (&d)[20], uint32_t a0, uint32_t a1, uint32_t a2, uint32_t a3, uint64_t db, int scale_d) {
  asm volatile("{\n.reg .pred p;\nsetp.ne.b32 p, %25, 0;\n"
    "wgmma.mma_async.sync.aligned.m64n40k16.f32.bf16.bf16 {%0, %1, %2, %3, %4, %5, %6, %7, %8, %9, %10, %11, %12, %13, %14, %15, %16, %17, %18, %19}, {%20, %21, %22, %23}, %24, p, %27, 1, %26;\n}\n"
    : "+f"(d[0]), "+f"(d[1]), "+f"(d[2]), "+f"(d[3]), "+f"(d[4]), "+f"(d[5]), "+f"(d[6]), "+f"(d[7]), "+f"(d[8]), "+f"(d[9]), "+f"(d[10]), "+f"(d[11]), "+f"(d[12]), "+f"(d[13]), "+f"(d[14]), "+f"(d[15]), "+f"(d[16]), "+f"(d[17]), "+f"(d[18]), "+f"(d[19])
    : "r"(a0), "r"(a1), "r"(a2), "r"(a3), "l"(db), "r"(scale_d), "n"(TB), "n"(SA));
}
template<int TB> __device__ __forceinline__ void wgmma_hrs_n64(uint32_t (&d)[16], uint32_t a0, uint32_t a1, uint32_t a2, uint32_t a3, uint64_t db, int scale_d) {
  asm volatile("{\n.reg .pred p;\nsetp.ne.b32 p, %21, 0;\n"
    "wgmma.mma_async.sync.aligned.m64n64k16.f16.f16.f16 {%0, %1, %2, %3, %4, %5, %6, %7, %8, %9, %10, %11, %12, %13, %14, %15}, {%16, %17, %18, %19}, %20, p, 1, 1, %22;\n}\n"
    : "+r"(d[0]), "+r"(d[1]), "+r"(d[2]), "+r"(d[3]), "+r"(d[4]), "+r"(d[5]), "+r"(d[6]), "+r"(d[7]), "+r"(d[8]), "+r"(d[9]), "+r"(d[10]), "+r"(d[11]), "+r"(d[12]), "+r"(d[13]), "+r"(d[14]), "+r"(d[15])
    : "r"(a0), "r"(a1), "r"(a2), "r"(a3), "l"(db), "r"(scale_d), "n"(TB));
}
template<int TB> __device__ __forceinline__ void wgmma_hrs_n32(uint32_t (&d)[8], uint32_t a0, uint32_t a1, uint32_t a2, uint32_t a3, uint64_t db, int scale_d) {
  asm volatile("{\n.reg .pred p;\nsetp.ne.b32 p, %13, 0;\n"
    "wgmma.mma_async.sync.aligned.m64n32k16.f16.f16.f16 {%0, %1, %2, %3, %4, %5, %6, %7}, {%8, %9, %10, %11}, %12, p, 1, 1, %14;\n}\n"
    : "+r"(d[0]), "+r"(d[1]), "+r"(d[2]), "+r"(d[3]), "+r"(d[4]), "+r"(d[5]), "+r"(d[6]), "+r"(d[7])
    : "r"(a0), "r"(a1), "r"(a2), "r"(a3), "l"(db), "r"(scale_d), "n"(TB));
}

__device__ __align__(128) const uint32_t c_thr[1536] = {
  0x33fb33ff,0xa49c9de4,0x33273352,0xaf2cae76,0x33e233f1,0xa96ca7bd,0x32c432f7,0xb045afdd,0x33b733cf,0xac3eaaf7,0x3250328c,0xb0eab099,
  0x3378339a,0xadbcacff,0x31cd3211,0xb182b137,0x33d033fb,0xaadea46a,0x299e2d17,0xb3e0b396,0x32fb337a,0xafd2adb1,0xa78b1f76,0xb3f2b3ff,
  0x318b3254,0xb1c5b0e5,0xae6bac32,0xb354b3b8,0x2f4230a3,0xb321b285,0xb133b040,0xb215b2c7,0x337c33f2,0xada5a759,0xb179afc8,0xb1d6b2fe,
  0x31463293,0xb204b08e,0xb394b2ba,0xad23b055,0x2b402f4e,0xb3cbb31e,0xb3e4b3f9,0x293ba533,0xac269c52,0xb3bab400,0xb258b357,0x30e02e5f,
  0x330133e5,0xafbda922,0xb3f3b3c9,0x2727ab59,0x2deb314a,0xb36fb200,0xb194b32f,0x31bc2f0a,0xacdb2084,0xb39fb3ff,0xa565aea4,0x33f93347,
  0xb2b6b0db,0xb05ab25c,0x30892c1a,0x329733bc,0x326033d4,0xb0d6aa94,0xb00ab29b,0x32e83084,0x20e82f64,0xb3feb318,0x2d8da597,0x338133f8,
  0xb1fcae48,0xb14fb35c,0x339031b8,0x2d3a3199,0xb3e6b3ae,0x2909ac7b,0x32d133f4,0xb030a6f5,0x319d33bf,0xb1b3ac02,0x2e3ca874,0x335e33ec,
  0xacc32b89,0xb3a3b3c6,0x33f83276,0x25c930b7,0xb3dcb1f8,0xaa01b154,0x30653335,0xb2b0aef4,0xb107b383,0x32392d81,0xafa6214d,0xb307b3fe,
  0x30bc33a5,0xb273acb7,0x33c5311b,0x2ba23229,0xb0cc94b6,0xb267b400,0x30153360,0xb2e1ae31,0xb385b3ab,0x2d76ac93,0xb166a691,0xb1e7b3f5,
  0x22deb06a,0x33fd32ac,0xb337b3da,0x2ee8aa19,0x2f853387,0xb310ad6a,0x322d33fe,0xb1162216,0xb2a9abd3,0xb06fb3c2,0xb07428a6,0xb2a5b3ea,
  0xb111b3e9,0x323128be,0xb30db3c3,0x2f90abba,0x31aa227a,0x31a633fd,0x2e25ad5e,0x33633389,0x2d6a3365,0xb387ae1a,0xa21631aa,0xb3feb1a6,
  0xb3c2af85,0xabd3b310,0xb3eab22d,0x28a6b116,0xa8beb2a9,0x33e9306f,0x2bbab074,0x33c332a5,0x33fd3111,0x227a3231,0x3389330d,0xad5e2f90,
  0x2a63333f,0xb3d7aec6,0xb2a2a1b1,0xb07ab3fe,0xb3f7b158,0x25fbb1f4,0xacb7b38b,0x33a52d52,0x2e0eb025,0x336832d8,0x340030bc,0x14b63273,
  0x323533c0,0xb10c2beb,0xac9330cc,0xb3abb267,0x23433316,0xb3fdaf6f,0xb38eb225,0x2d46b11f,0xb342b29e,0x2ebbb07f,0x31e3aa7c,0x316b33d6,
  0x3264a6c3,0x30d133f5,0x2c0233ac,0xb3bfac87,0x28f0336a,0xb3e7ae02,0xb3c6b19d,0x2b89b1b3,0xa59732e8,0xb3f8b00a,0xaccfb3ed,0x33a1285b,
  0xb1b8b381,0x3199ad8d,0x336c31df,0xadf73170,0x33f42d3a,0x26f53390,0xb30423a7,0xafb2b3fc,0xb05f3030,0xb2b3b2d1,0x29e8b27a,0x33dd30b2,
  0xab5932b6,0xb3c9b05a,0x30adb089,0x327e3297,0xaf0ab3f3,0x332fa727,0x240633b0,0xb3fcac6f,0x33473194,0xaea431bc,0xb174b359,0x31daae54,
  0xb3bca565,0xac1ab3f9,0x33ee2f59,0xa842331b,0xaddf3281,0xb371b0a8,0x34002b40,0x1c5233cb,0xa759b3ef,0x33f22829,0xb2fe2c26,0xafc8b3ba,
  0x308e337c,0xb2932da5,0x3055b179,0x32ba31d6,0xb31eb146,0x2f4eb204,0xa5333394,0xb3f9ad23,0xaff33249,0xb2f1b0f3,0x30e532fb,0xb2542fd2,
  0x2b28b373,0x33cc2dd4,0xb285b18b,0x30a3b1c5,0x246a33fa,0xb3fba500,0x33962f42,0xad173321,0xadb1b3d0,0x337aaade,0xb3ffa99e,0x1f76b3e0,
  0xb0ee320d,0xb24db13c,0xac4b3398,0xb3b5ad0b,0x304ab289,0x32c1309e,0x2985b3ce,0x33e12b0f,0xaf3732f4,0xb324afe8,0xa4ce33f0,0xb3faa7ef,
  0x2dc8b34f,0x33762e82,0x9de4b3ff,0x33ff1ead,0xb1c931cd,0xb186b182,0xb3762e82,0xadc8b34f,0x324db13c,0x30ee320d,0x33b5ad0b,0x2c4b3398,
  0xb2c1309e,0xb04ab289,0xb3e12b0f,0xa985b3ce,0x3324afe8,0x2f3732f4,0x33faa7ef,0x24ce33f0,0xb285318b,0xb0a3b1c5,0xb2c7ae6b,0x3040b354,
  0x3396af42,0x2d173321,0x31413133,0xb2093215,0xb3ff299e,0x9f76b3e0,0xae8db2bd,0x334cb050,0x33b8278b,0xac3233f2,0x281033b3,0xb3ef2c57,
  0xb31e3146,0xaf4eb204,0xa533b394,0x33f9ad23,0x3400ab40,0x9c5233cb,0xae5f33e4,0xb357a93b,0xb2feac26,0x2fc8b3ba,0x3245b258,0x30f830e0,
  0x30553179,0xb2ba31d6,0xb3df2e99,0xa9b6b34a,0xb39230fd,0xad2fb241,0x3200b301,0x314a2fbd,0x337f1b11,0xad993400,0xb3ff2deb,0xa084b36f,
  0xb005b129,0x32ebb21d,0x325c2cdb,0xb0db339f,0xa92233de,0xb3e529cf,0xab59b2b6,0x33c9b05a,0xb3dd30b2,0xa9e8b27a,0x33d4ab71,0xaa9433c8,
  0x32212c0e,0xb12433bd,0xaf64b0d6,0x3318b260,0x197fb345,0x3400aeaf,0xae4833fe,0xb35c20e8,0xb23d3332,0xb102aeff,0x33aeb14f,0x2c7b31fc,
  0xb3fe3065,0xa14db2b0,0x2ebb307f,0xb342329e,0x300f2fa6,0xb2e53307,0x30d1b3f5,0x326426c3,0x302ab400,0x32d517db,0xb3e72e02,0x28f0b36a,
  0xb3fd2f6f,0x2343b316,0x2d46311f,0xb38e3225,0xb3f53015,0x2691b2e1,0xaf9b33eb,0xb30a288d,0x2a193166,0xb3da31e7,0x33d7aec6,0xaa63333f,
  0x3313b337,0x2f7a2ee8,0xa5fbb1f4,0x33f7b158,0xb1a1a8d7,0x31afb3e8,0xb36832d8,0xae0eb025,0xb3c22f85,0x2bd3b310,0xb3ea322d,0xa8a6b116,
  0xa8be32a9,0xb3e9306f,0x2bba3074,0xb3c332a5,0x33fdb111,0xa27a3231,0x3389b30d,0x2d5e2f90,0xa216b1aa,0x33feb1a6,0xaed2ae25,0x333db363,
  0xb3652edd,0x2e1ab33a,0xb1aa227a,0x31a6b3fd,0xaf853387,0xb3102d6a,0xb22d33fe,0xb116a216,0x32a9abd3,0xb06f33c2,0x307428a6,0xb2a533ea,
  0x3111b3e9,0x3231a8be,0x330db3c3,0x2f902bba,0xb2e12e31,0x3015b360,0x288db1a1,0x33ebb1af,0xb1e733f5,0xb1662691,0xb33f2f9b,0x2ec6b30a,
  0x2ee82a19,0xb33733da,0xb15833d7,0xb1f42a63,0x33e8b313,0x28d72f7a,0x302525fb,0xb2d833f7,0xb2392d81,0x3107b383,0x3307b3fe,0x2fa6214d,
  0xb35e33ec,0xae3ca874,0x97dbb00f,0x3400b2e5,0xa5c930b7,0xb3f83276,0xb316302a,0x2f6fb2d5,0x32b0aef4,0xb0653335,0xb29e33fd,0xb07f2343,
  0xb1702ccf,0x31dfb3a1,0x3345b124,0xaeaf3221,0xb3fc336c,0xa3a7adf7,0x3332b400,0x2eff997f,0xb0b23304,0xb27a2fb2,0x2b71b102,0x33c8b23d,
  0x2c0e29e8,0xb3bd33dd,0xb0d62a94,0x3260b3d4,0xb0892c1a,0x3297b3bc,0x2aad2842,0xb3d333ee,0xb3b0327e,0x2c6fb0ad,0x3241b035,0xb0fd32ce,
  0xb35933fc,0xae542406,0x3400b392,0x1b112d2f,0xaf5931da,0xb31b3174,0x321db37f,0x3129ad99,0xaf152ac6,0x332cb3d2,0xb1463293,0xb204308e,
  0xb281312e,0x30a8b219,0xab402f4e,0xb3cb331e,0xb3ef3371,0x2829addf,0x2c269c52,0xb3ba3400,0xb37c33f2,0xada52759,0x3179afc8,0xb1d632fe,
  0xacf32953,0x339cb3e3,0xb3fa33cc,0x2500ab28,0xb0942f21,0x3290b32a,0xb3d033fb,0xaade246a,0xb249317d,0x30f3b1d2,0xb2fb337a,0xafd22db1,
  0xb37332f1,0x2dd4aff3,0xb18b3254,0xb1c530e5,0xa96c27bd,0x33e2b3f1,0xb0452fdd,0x32c4b2f7,0xac3e2af7,0x33b7b3cf,0xb0ea3099,0x3250b28c,
  0xadbc2cff,0x3378b39a,0xb1823137,0x31cdb211,0xaf2c2e76,0x3327b352,0xb20d31c9,0x313cb186,0x313c3186,0xb20db1c9,0x2d0b2dc8,0xb398b376,
  0x309e30ee,0xb289b24d,0x2b0f2c4b,0xb3ceb3b5,0x2fe8304a,0xb2f4b2c1,0x27ef2985,0xb3f0b3e1,0x2e822f37,0xb34fb324,0x1ead24ce,0xb3ffb3fa,
  0xb2bdb209,0xb050b141,0xb290b32a,0x30942f21,0xb3b3b34c,0xac57ae8d,0xb0f3b1d2,0x3249317d,0xb400b3ef,0x1d1ba810,0xadd4aff3,0x337332f1,
  0xb39cb3e3,0x2cf32953,0xa500ab28,0x33fa33cc,0xae99b0f8,0x334a3245,0x33ff33b2,0x201f2c63,0x2438a9b6,0x33fc33df,0x332c33d2,0xaf15aac6,
  0x303a2ce7,0x32cb339e,0x30a83219,0xb281b12e,0x32ee31c0,0x2ffe3190,0x28292ddf,0xb3efb371,0x33b0327e,0x2c6f30ad,0xb241b035,0xb0fdb2ce,
  0x335933fc,0xae54a406,0xb400b392,0x1b11ad2f,0x2f5931da,0xb31bb174,0xb21db37f,0x31292d99,0xaaad2842,0xb3d3b3ee,0xa9cfb005,0x33de32eb,
  0x285b305f,0xb3edb2b3,0x2c0ea9e8,0x33bd33dd,0xb170accf,0xb1dfb3a1,0x33453124,0x2eaf3221,0xb3fcb36c,0x23a7adf7,0x33323400,0xaeff997f,
  0xb0b2b304,0x327a2fb2,0x2b713102,0xb3c8b23d,0xb400b2e5,0x17dbb00f,0x2e023264,0xb36ab0d1,0xaf6fb2d5,0x3316302a,0xb11fa8f0,0xb225b3e7,
  0x307f2343,0x329e33fd,0xb3d6b38e,0x2a7cad46,0x33f53342,0xa6c32ebb,0xac87b1e3,0x33ac316b,0x28d7af7a,0x33e83313,0xb2d8b3f7,0x3025a5fb,
  0x33eb31af,0x288d31a1,0x2bebae0e,0x33c03368,0x2ec6330a,0xb33faf9b,0x33fe3235,0x21b1310c,0xb1f4aa63,0xb158b3d7,0x2d5232a2,0xb38bb07a,
  0x33a7333d,0xacab2ed2,0x33f63162,0x262d31eb,0xaa4b301a,0xb3d8b2de,0x2a32326b,0xb3d9b0c7,0xb3f6b26f,0x265fb0c1,0xb3a9b020,0xac9fb2db,
  0x0e48b15d,0x340031f0,0xae1ab33a,0x33652edd,0xaed22e25,0xb33db363,0xb1eb0e48,0xb162b400,0xb2deb3a7,0x301aacab,0xb0c7b3f6,0x326b262d,
  0x30c1aa4b,0x326f33d8,0x32db2a32,0x302033d9,0x31f033f6,0xb15d265f,0x2edd33a9,0xb33aac9f,0xb2acb385,0x306aad76,0x2a19b166,0x33da31e7,
  0x3229a2de,0x311b33fd,0x33133337,0xaf7a2ee8,0x2e3133c5,0xb360aba2,0xb1a128d7,0xb1afb3e8,0xb3f5b015,0xa691b2e1,0xaf9bb3eb,0x330a288d,
  0x3154acc3,0x31f833a3,0x2ef433f8,0xb335a5c9,0x2d8133dc,0xb383aa01,0xb3feb065,0x214db2b0,0xb3ecb107,0x2874b239,0x300fafa6,0x32e53307,
  0x30b7ae3c,0x3276335e,0x302a3400,0xb2d517db,0x312433bd,0xb2212c0e,0xb318b260,0x2f64b0d6,0xb400aeaf,0x997fb345,0x335c20e8,0x2e4833fe,
  0x3102aeff,0x323d3332,0xac7b31fc,0xb3aeb14f,0x2a9433c8,0xb3d4ab71,0xb084b3e6,0x329ba909,0xb2ce2aad,0xb035b3d3,0x33e529cf,0x292233de,
  0x2d2fb241,0x339230fd,0xb14a2fbd,0xb200b301,0x2d993400,0xb37f1b11,0x2084b36f,0x33ff2deb,0xb2ebb21d,0x3005b129,0x30db339f,0xb25c2cdb,
  0xae5fb3e4,0x3357a93b,0xb190303a,0xb1c0b2cb,0x32453258,0xb0f830e0,0x2c63b2ee,0x33b22ffe,0xb3dfae99,0x29b6b34a,0x2ac633ff,0xb3d2a01f,
  0x339ea438,0x2ce733fc,0xb12eb32c,0x3219af15,0x33b8a78b,0x2c3233f2,0x2810b3b3,0x33ef2c57,0xb2c72e6b,0xb040b354,0x29533400,0xb3e31d1b,
  0x3141b133,0x32093215,0xaf21b39c,0x332aacf3,0xae8d32bd,0xb34cb050,0x317d3290,0xb1d23094,0x27bd33fb,0xb3f1249c,0x2fdd3327,0xb2f72f2c,
  0xaaf7b3e2,0x33cfa96c,0xb099b2c4,0x328cb045,0x2cff33b7,0xb39a2c3e,0x31373250,0xb21130ea,0xae76b378,0x3352adbc,0xb1c9b1cd,0x3186b182,
  0xb3ff1ead,0x1de4b3ff,0xb352adbc,0x2e76b378,0x33f1249c,0xa7bd33fb,0x32f72f2c,0xafdd3327,0xb3cfa96c,0x2af7b3e2,0xb28cb045,0x3099b2c4,
  0x339a2c3e,0xacff33b7,0x321130ea,0xb1373250,0x2953b400,0x33e31d1b,0x33ccadd4,0x2b283373,0xaf21339c,0xb32aacf3,0xb3fb2500,0x246ab3fa,
  0x317db290,0x31d23094,0x337a2ade,0xadb133d0,0xb2f130f3,0xaff3b249,0xb254afd2,0x30e5b2fb,0x339e2438,0xace733fc,0xb12e332c,0xb219af15,
  0xb190b03a,0x31c0b2cb,0x3371b0a8,0x2ddf3281,0x2c6332ee,0xb3b22ffe,0xb3f22829,0x2759b3ef,0x2ac6b3ff,0x33d2a01f,0x32932da5,0xb08e337c,
  0xaf0a33f3,0xb32fa727,0x2406b3b0,0x33fcac6f,0x3347b194,0x2ea431bc,0xb1743359,0xb1daae54,0xb3bc2565,0x2c1ab3f9,0x33eeaf59,0x2842331b,
  0x30ad3089,0xb27e3297,0xb2ceaaad,0x3035b3d3,0xb29ba909,0x3084b3e6,0x305f3030,0xb2b332d1,0x259732e8,0xb3f8300a,0x2ccfb3ed,0x33a1a85b,
  0x31b8b381,0x31992d8d,0xb36c31df,0xadf7b170,0xb3f42d3a,0x26f5b390,0x330423a7,0xafb233fc,0x316bb3d6,0x31e32a7c,0xb3832a01,0x2d81b3dc,
  0xb3bf2c87,0x2c02b3ac,0x28743239,0xb3ec3107,0x2b8931b3,0xb3c6319d,0x3276b35e,0x30b72e3c,0x31f8b3a3,0x31542cc3,0xb33525c9,0x2ef4b3f8,
  0x310c2beb,0xb23533c0,0x33abb267,0x2c9330cc,0x307ab3fe,0x32a2a1b1,0xb06aad76,0x32acb385,0xb3a52d52,0x2cb7b38b,0xb11b33fd,0xb229a2de,
  0x94b63273,0xb40030bc,0x3360aba2,0xae3133c5,0xb2de33a7,0xb01aacab,0xb0c733f6,0xb26b262d,0x30c12a4b,0xb26f33d8,0x32dbaa32,0xb02033d9,
  0x31f0b3f6,0x315d265f,0x2eddb3a9,0x333aac9f,0xb1eb8e48,0x3162b400,0xb3872e1a,0x2d6ab365,0xae25ad5e,0x3363b389,0x8e48b15d,0x3400b1f0,
  0xb3a7333d,0xacabaed2,0xb3f63162,0x262db1eb,0x2a4b301a,0xb3d832de,0xaa32326b,0xb3d930c7,0x33f6b26f,0x265f30c1,0x33a9b020,0xac9f32db,
  0x33c0b368,0x2beb2e0e,0x30cc94b6,0xb2673400,0x21b1b10c,0x33feb235,0x3385b3ab,0x2d762c93,0xb38b307a,0x2d52b2a2,0xa2deb06a,0x33fdb2ac,
  0xb0bc33a5,0xb2732cb7,0xb3c5311b,0x2ba2b229,0x26c32ebb,0xb3f53342,0xb3ac316b,0x2c87b1e3,0x336ab0d1,0xae023264,0xb19d33bf,0xb1b32c02,
  0x3225b3e7,0x311fa8f0,0x2cc32b89,0xb3a333c6,0xaa7cad46,0x33d6b38e,0x33dcb1f8,0xaa013154,0xb3fe3318,0x20e8af64,0x3381b3f8,0x2d8d2597,
  0xb14f335c,0xb1fc2e48,0x2d3ab199,0x3390b1b8,0x29092c7b,0xb3e633ae,0xb03026f5,0x32d1b3f4,0x32e8b084,0xb00a329b,0xb3ed32b3,0x285bb05f,
  0x29cfb005,0x33deb2eb,0xb05a325c,0xb2b630db,0xafbd2922,0x3301b3e5,0x27272b59,0xb3f333c9,0xb36f3200,0x2debb14a,0x31bcaf0a,0xb194332f,
  0xb39f33ff,0xacdba084,0x33f9b347,0xa5652ea4,0x3394b2ba,0xad233055,0xa438a9b6,0x33fcb3df,0x33e4b3f9,0x293b2533,0xb03a2ce7,0x32cbb39e,
  0x3258b357,0x30e0ae5f,0xb2ee31c0,0x2ffeb190,0x2e99b0f8,0x334ab245,0xb3ff33b2,0x201fac63,0xaf4230a3,0xb3213285,0x3133b040,0xb21532c7,
  0xa99e2d17,0xb3e03396,0x32bdb209,0xb0503141,0x278b1f76,0xb3f233ff,0x33b3b34c,0xac572e8d,0x2e6bac32,0xb35433b8,0x3400b3ef,0x1d1b2810,
  0xb289324d,0x309eb0ee,0xb3ce33b5,0x2b0fac4b,0xb2f432c1,0x2fe8b04a,0xb3f033e1,0x27efa985,0xb34f3324,0x2e82af37,0xb3ff33fa,0x1eada4ce,
  0xb3983376,0x2d0badc8,0xb3fb33ff,0xa49c1de4,0x351c35f6,0xac93a617,0xb8a3b93c,0x308d2a16,0x32f43448,0xb160afa5,0xb6a4b7fe,0x353a3389,
  0x2fa53160,0xb448b2f4,0xb389b53a,0x37fe36a4,0x26172c93,0xb5f6b51c,0xaa16b08d,0x393c38a3,0x34c3358c,0xac47a5b2,0xb85fb8f3,0x304229b1,
  0x327e33fd,0xb106af26,0xb63cb785,0x34e7330f,0x2f263106,0xb3fdb27e,0xb30fb4e7,0x3785363c,0x25b22c47,0xb58cb4c3,0xa9b1b042,0x38f3385f,
  0x346a3523,0xabf6a54d,0xb81ab8a8,0x2fef294d,0x3209336b,0xb0acaea7,0xb5d4b70a,0x34933294,0x2ea730ac,0xb36bb209,0xb294b493,0x370a35d4,
  0x254d2bf6,0xb523b46a,0xa94dafef,0x38a8381a,0x341334bc,0xab5fa4e9,0xb7a6b85a,0x2f5928e8,0x319432da,0xb052ae28,0xb56ab68d,0x343e3219,
  0x2e283052,0xb2dab194,0xb219b43e,0x368d356a,0x24e92b5f,0xb4bcb413,0xa8e8af59,0x385a37a6,0x33783456,0xaac8a484,0xb715b80a,0x2ec32884,
  0x3120324a,0xaff2ada9,0xb4ffb60e,0x33d3319e,0x2da92ff2,0xb24ab120,0xb19eb3d3,0x360e34ff,0x24842ac8,0xb456b378,0xa884aec3,0x380a3715,
  0x32cd33e3,0xaa31a420,0xb682b76f,0x2e2d281f,0x30ac31bb,0xaf3fad2a,0xb493b58d,0x33283122,0x2d2a2f3f,0xb1bbb0ac,0xb122b328,0x358d3493,
  0x24202a31,0xb3e3b2cd,0xa81fae2d,0x376f3682,0x3223331c,0xa999a376,0xb5ebb6c6,0x2d972776,0x3039312d,0xae8dacac,0xb426b50b,0x327c30a6,
  0x2cac2e8d,0xb12db039,0xb0a6b27c,0x350b3426,0x23762999,0xb31cb223,0xa776ad97,0x36c635eb,0x317a3257,0xa902a2ad,0xb552b61a,0x2d0026ad,
  0x2f8c309f,0xaddcac2e,0xb371b487,0x31cf3029,0x2c2e2ddc,0xb09faf8c,0xb029b1cf,0x34873371,0x22ad2902,0xb257b17a,0xa6adad00,0x361a3552,
  0x30d23194,0xa86ba1e4,0xb4b7b56a,0x2c6a25e4,0x2ea73012,0xad2aab5f,0xb294b402,0x31222f59,0x2b5f2d2a,0xb012aea7,0xaf59b122,0x34023294,
  0x21e4286b,0xb194b0d2,0xa5e4ac6a,0x356a34b7,0x302c30d2,0xa7a9a11b,0xb41ab4b7,0x2ba7251b,0x2dc22f0c,0xac79aa63,0xb1b6b2f7,0x30742e5f,
  0x2a632c79,0xaf0cadc2,0xae5fb074,0x32f731b6,0x211b27a9,0xb0d2b02c,0xa51baba7,0x34b7341a,0x2f0c3012,0xa67ba052,0xb2f7b402,0x2a7a2452,
  0x2cde2df5,0xab91a967,0xb0d7b1e8,0x2f8b2d65,0x29672b91,0xadf5acde,0xad65af8b,0x31e830d7,0x2052267b,0xb012af0c,0xa452aa7a,0x340232f7,
  0x2dc22ea7,0xa54d9f12,0xb1b6b294,0x294d2311,0x2bf62cde,0xaa31a86b,0xafefb0d7,0x2e2d2c6a,0x286b2a31,0xacdeabf6,0xac6aae2d,0x30d72fef,
  0x1f12254d,0xaea7adc2,0xa311a94d,0x329431b6,0x2c792d2a,0xa4209d7f,0xb074b122,0x281f217f,0x2a312b91,0xa8d0a6e0,0xae2daf8b,0x2cce2ade,
  0x26e028d0,0xab91aa31,0xaadeacce,0x2f8b2e2d,0x1d7f2420,0xad2aac79,0xa17fa81f,0x31223074,0x2a632b5f,0xa1e49bdb,0xae5faf59,0x25e41fdb,
  0x286b2967,0xa6e0a4e9,0xac6aad65,0x2ade28e8,0x24e926e0,0xa967a86b,0xa8e8aade,0x2d652c6a,0x1bdb21e4,0xab5faa63,0x9fdba5e4,0x2f592e5f,
  0x27a9286b,0x9f1298b6,0xaba7ac6a,0x23111cb6,0x254d267b,0xa420a1e4,0xa94daa7a,0x281f25e4,0x21e42420,0xa67ba54d,0xa5e4a81f,0x2a7a294d,
  0x18b61f12,0xa86ba7a9,0x9cb6a311,0x2c6a2ba7,0x211b21e4,0x98b69248,0xa51ba5e4,0x1cb61648,0x1f122052,0x9d7f9bdb,0xa311a452,0x217f1fdb,
  0x1bdb1d7f,0xa0529f12,0x9fdba17f,0x24522311,0x124818b6,0xa1e4a11b,0x96489cb6,0x25e4251b,0xa11ba1e4,0x18b61248,0x251b25e4,0x9cb69648,
  0x9f12a052,0x1d7f1bdb,0x23112452,0xa17f9fdb,0x9bdb9d7f,0x20521f12,0x1fdb217f,0xa452a311,0x924898b6,0x21e4211b,0x16481cb6,0xa5e4a51b,
  0xa7a9a86b,0x1f1218b6,0x2ba72c6a,0xa3119cb6,0xa54da67b,0x242021e4,0x294d2a7a,0xa81fa5e4,0xa1e4a420,0x267b254d,0x25e4281f,0xaa7aa94d,
  0x98b69f12,0x286b27a9,0x1cb62311,0xac6aaba7,0xaa63ab5f,0x21e41bdb,0x2e5f2f59,0xa5e49fdb,0xa86ba967,0x26e024e9,0x2c6a2d65,0xaadea8e8,
  0xa4e9a6e0,0x2967286b,0x28e82ade,0xad65ac6a,0x9bdba1e4,0x2b5f2a63,0x1fdb25e4,0xaf59ae5f,0xac79ad2a,0x24201d7f,0x30743122,0xa81fa17f,
  0xaa31ab91,0x28d026e0,0x2e2d2f8b,0xacceaade,0xa6e0a8d0,0x2b912a31,0x2ade2cce,0xaf8bae2d,0x9d7fa420,0x2d2a2c79,0x217f281f,0xb122b074,
  0xadc2aea7,0x254d1f12,0x31b63294,0xa94da311,0xabf6acde,0x2a31286b,0x2fef30d7,0xae2dac6a,0xa86baa31,0x2cde2bf6,0x2c6a2e2d,0xb0d7afef,
  0x9f12a54d,0x2ea72dc2,0x2311294d,0xb294b1b6,0xaf0cb012,0x267b2052,0x32f73402,0xaa7aa452,0xacdeadf5,0x2b912967,0x30d731e8,0xaf8bad65,
  0xa967ab91,0x2df52cde,0x2d652f8b,0xb1e8b0d7,0xa052a67b,0x30122f0c,0x24522a7a,0xb402b2f7,0xb02cb0d2,0x27a9211b,0x341a34b7,0xaba7a51b,
  0xadc2af0c,0x2c792a63,0x31b632f7,0xb074ae5f,0xaa63ac79,0x2f0c2dc2,0x2e5f3074,0xb2f7b1b6,0xa11ba7a9,0x30d2302c,0x251b2ba7,0xb4b7b41a,
  0xb0d2b194,0x286b21e4,0x34b7356a,0xac6aa5e4,0xaea7b012,0x2d2a2b5f,0x32943402,0xb122af59,0xab5fad2a,0x30122ea7,0x2f593122,0xb402b294,
  0xa1e4a86b,0x319430d2,0x25e42c6a,0xb56ab4b7,0xb17ab257,0x290222ad,0x3552361a,0xad00a6ad,0xaf8cb09f,0x2ddc2c2e,0x33713487,0xb1cfb029,
  0xac2eaddc,0x309f2f8c,0x302931cf,0xb487b371,0xa2ada902,0x3257317a,0x26ad2d00,0xb61ab552,0xb223b31c,0x29992376,0x35eb36c6,0xad97a776,
  0xb039b12d,0x2e8d2cac,0x3426350b,0xb27cb0a6,0xacacae8d,0x312d3039,0x30a6327c,0xb50bb426,0xa376a999,0x331c3223,0x27762d97,0xb6c6b5eb,
  0xb2cdb3e3,0x2a312420,0x3682376f,0xae2da81f,0xb0acb1bb,0x2f3f2d2a,0x3493358d,0xb328b122,0xad2aaf3f,0x31bb30ac,0x31223328,0xb58db493,
  0xa420aa31,0x33e332cd,0x281f2e2d,0xb76fb682,0xb378b456,0x2ac82484,0x3715380a,0xaec3a884,0xb120b24a,0x2ff22da9,0x34ff360e,0xb3d3b19e,
  0xada9aff2,0x324a3120,0x319e33d3,0xb60eb4ff,0xa484aac8,0x34563378,0x28842ec3,0xb80ab715,0xb413b4bc,0x2b5f24e9,0x37a6385a,0xaf59a8e8,
  0xb194b2da,0x30522e28,0x356a368d,0xb43eb219,0xae28b052,0x32da3194,0x3219343e,0xb68db56a,0xa4e9ab5f,0x34bc3413,0x28e82f59,0xb85ab7a6,
  0xb46ab523,0x2bf6254d,0x381a38a8,0xafefa94d,0xb209b36b,0x30ac2ea7,0x35d4370a,0xb493b294,0xaea7b0ac,0x336b3209,0x32943493,0xb70ab5d4,
  0xa54dabf6,0x3523346a,0x294d2fef,0xb8a8b81a,0xb4c3b58c,0x2c4725b2,0x385f38f3,0xb042a9b1,0xb27eb3fd,0x31062f26,0x363c3785,0xb4e7b30f,
  0xaf26b106,0x33fd327e,0x330f34e7,0xb785b63c,0xa5b2ac47,0x358c34c3,0x29b13042,0xb8f3b85f,0xb51cb5f6,0x2c932617,0x38a3393c,0xb08daa16,
  0xb2f4b448,0x31602fa5,0x36a437fe,0xb53ab389,0xafa5b160,0x344832f4,0x3389353a,0xb7feb6a4,0xa617ac93,0x35f6351c,0x2a16308d,0xb93cb8a3,
};
__device__ __align__(128) const uint32_t c_img[2560] = {
  0x326d31ed,0x333b32dd,0x33c33388,0x33fe33ea,0x33c331ed,0x31ed33c3,0xa8b22d64,0xb33bb0c4,0x33ea31ed,0xad64301d,0xb2ddb388,0x315fa8b2,
  0x32dd31ed,0xb3feabc6,0x326dad64,0xad64326d,0x30c431ed,0xaed7b2dd,0x2bc63388,0xa248b3ea,0x2bc631ed,0x315fb3c3,0xb3ea2d64,0x2ed730c4,
  0xa8b231ed,0x3388b01d,0x301db388,0xb1ed28b2,0xb01d31ed,0x22482bc6,0x30c4ad64,0x3388b26d,0x33ea33fe,0x338833c3,0x32dd333b,0x31ed326d,
  0xb2ddb3fe,0xa248b01d,0x326d2ed7,0x338833ea,0x30c433fe,0xb33babc6,0xabc6b33b,0x33fe30c4,0xabc6b3fe,0x31ed32dd,0xb3eaaed7,0x333ba8b2,
  0xa8b233fe,0x2d64b3c3,0xb01d333b,0x315fb26d,0x301db3fe,0xb3fe301d,0x30c42ed7,0x2d64b3ea,0xb26d33fe,0x2ed72bc6,0x33c3b33b,0xa248b0c4,
  0x33c3b3fe,0x315fb2dd,0x28b2aed7,0xaed728b2,0xb0c4b15f,0xaed7b01d,0xabc6ad64,0xa248a8b2,0xabc6b15f,0x315f2bc6,0x33ea3388,0x2ed7326d,
  0x28b2b15f,0x338832dd,0xb01d2d64,0xb1edb3ea,0x301db15f,0x224833c3,0xb0c4b388,0x338830c4,0x326db15f,0xb33b301d,0x33c3ad64,0xb3fe28b2,
  0x33c3b15f,0xb1edabc6,0xa8b23388,0x333bb26d,0x33eab15f,0x2d64b2dd,0xb2dd2d64,0xb15f33ea,0x32ddb15f,0x33feb3c3,0x326db388,0x2d64b0c4,
  0x28b22248,0x2d642bc6,0x301d2ed7,0x315f30c4,0xb01da248,0xb3feb2dd,0xb0c4b33b,0x2d64a8b2,0x326d2248,0x2ed733c3,0xb3c3aed7,0xa248b26d,
  0xb3c3a248,0x315fb01d,0xa8b2333b,0xaed7b3ea,0x33ea2248,0xb388abc6,0x32dd2ed7,0xb1edb0c4,0xb2dda248,0x224832dd,0x326db33b,0xb38828b2,
  0x30c42248,0x333bb3c3,0xabc6aed7,0xb3fe326d,0xabc6a248,0xb1ed301d,0xb3ea333b,0xb33b33ea,0xb26d31ed,0xb33b32dd,0xb3c33388,0xb3fe33ea,
  0xb3c331ed,0xb1ed33c3,0x28b22d64,0x333bb0c4,0xb3ea31ed,0x2d64301d,0x32ddb388,0xb15fa8b2,0xb2dd31ed,0x33feabc6,0xb26dad64,0x2d64326d,
  0xb0c431ed,0x2ed7b2dd,0xabc63388,0x2248b3ea,0xabc631ed,0xb15fb3c3,0x33ea2d64,0xaed730c4,0x28b231ed,0xb388b01d,0xb01db388,0x31ed28b2,
  0x301d31ed,0xa2482bc6,0xb0c4ad64,0xb388b26d,0xb3ea33fe,0xb38833c3,0xb2dd333b,0xb1ed326d,0x32ddb3fe,0x2248b01d,0xb26d2ed7,0xb38833ea,
  0xb0c433fe,0x333babc6,0x2bc6b33b,0xb3fe30c4,0x2bc6b3fe,0xb1ed32dd,0x33eaaed7,0xb33ba8b2,0x28b233fe,0xad64b3c3,0x301d333b,0xb15fb26d,
  0xb01db3fe,0x33fe301d,0xb0c42ed7,0xad64b3ea,0x326d33fe,0xaed72bc6,0xb3c3b33b,0x2248b0c4,0xb3c3b3fe,0xb15fb2dd,0xa8b2aed7,0x2ed728b2,
  0x30c4b15f,0x2ed7b01d,0x2bc6ad64,0x2248a8b2,0x2bc6b15f,0xb15f2bc6,0xb3ea3388,0xaed7326d,0xa8b2b15f,0xb38832dd,0x301d2d64,0x31edb3ea,
  0xb01db15f,0xa24833c3,0x30c4b388,0xb38830c4,0xb26db15f,0x333b301d,0xb3c3ad64,0x33fe28b2,0xb3c3b15f,0x31edabc6,0x28b23388,0xb33bb26d,
  0xb3eab15f,0xad64b2dd,0x32dd2d64,0x315f33ea,0xb2ddb15f,0xb3feb3c3,0xb26db388,0xad64b0c4,0xa8b22248,0xad642bc6,0xb01d2ed7,0xb15f30c4,
  0x301da248,0x33feb2dd,0x30c4b33b,0xad64a8b2,0xb26d2248,0xaed733c3,0x33c3aed7,0x2248b26d,0x33c3a248,0xb15fb01d,0x28b2333b,0x2ed7b3ea,
  0xb3ea2248,0x3388abc6,0xb2dd2ed7,0x31edb0c4,0x32dda248,0xa24832dd,0xb26db33b,0x338828b2,0xb0c42248,0xb33bb3c3,0x2bc6aed7,0x33fe326d,
  0x2bc6a248,0x31ed301d,0x33ea333b,0x333b33ea,0x30c4315f,0x2ed7301d,0x2bc62d64,0x224828b2,0x2bc6315f,0xb15fabc6,0xb3eab388,0xaed7b26d,
  0xa8b2315f,0xb388b2dd,0x301dad64,0x31ed33ea,0xb01d315f,0xa248b3c3,0x30c43388,0xb388b0c4,0xb26d315f,0x333bb01d,0xb3c32d64,0x33fea8b2,
  0xb3c3315f,0x31ed2bc6,0x28b2b388,0xb33b326d,0xb3ea315f,0xad6432dd,0x32ddad64,0x315fb3ea,0xb2dd315f,0xb3fe33c3,0xb26d3388,0xad6430c4,
  0xa8b2a248,0xad64abc6,0xb01daed7,0xb15fb0c4,0x301d2248,0x33fe32dd,0x30c4333b,0xad6428b2,0xb26da248,0xaed7b3c3,0x33c32ed7,0x2248326d,
  0x33c32248,0xb15f301d,0x28b2b33b,0x2ed733ea,0xb3eaa248,0x33882bc6,0xb2ddaed7,0x31ed30c4,0x32dd2248,0xa248b2dd,0xb26d333b,0x3388a8b2,
  0xb0c4a248,0xb33b33c3,0x2bc62ed7,0x33feb26d,0x2bc62248,0x31edb01d,0x33eab33b,0x333bb3ea,0x326d31ed,0x333b32dd,0x33c33388,0x33fe33ea,
  0x33c331ed,0x31ed33c3,0xa8b22d64,0xb33bb0c4,0x33ea31ed,0xad64301d,0xb2ddb388,0x315fa8b2,0x32dd31ed,0xb3feabc6,0x326dad64,0xad64326d,
  0x30c431ed,0xaed7b2dd,0x2bc63388,0xa248b3ea,0x2bc631ed,0x315fb3c3,0xb3ea2d64,0x2ed730c4,0xa8b231ed,0x3388b01d,0x301db388,0xb1ed28b2,
  0xb01d31ed,0x22482bc6,0x30c4ad64,0x3388b26d,0x33ea33fe,0x338833c3,0x32dd333b,0x31ed326d,0xb2ddb3fe,0xa248b01d,0x326d2ed7,0x338833ea,
  0x30c433fe,0xb33babc6,0xabc6b33b,0x33fe30c4,0xabc6b3fe,0x31ed32dd,0xb3eaaed7,0x333ba8b2,0xa8b233fe,0x2d64b3c3,0xb01d333b,0x315fb26d,
  0x301db3fe,0xb3fe301d,0x30c42ed7,0x2d64b3ea,0xb26d33fe,0x2ed72bc6,0x33c3b33b,0xa248b0c4,0x33c3b3fe,0x315fb2dd,0x28b2aed7,0xaed728b2,
  0xb0c4315f,0xaed7301d,0xabc62d64,0xa24828b2,0xabc6315f,0x315fabc6,0x33eab388,0x2ed7b26d,0x28b2315f,0x3388b2dd,0xb01dad64,0xb1ed33ea,
  0x301d315f,0x2248b3c3,0xb0c43388,0x3388b0c4,0x326d315f,0xb33bb01d,0x33c32d64,0xb3fea8b2,0x33c3315f,0xb1ed2bc6,0xa8b2b388,0x333b326d,
  0x33ea315f,0x2d6432dd,0xb2ddad64,0xb15fb3ea,0x32dd315f,0x33fe33c3,0x326d3388,0x2d6430c4,0x28b2a248,0x2d64abc6,0x301daed7,0x315fb0c4,
  0xb01d2248,0xb3fe32dd,0xb0c4333b,0x2d6428b2,0x326da248,0x2ed7b3c3,0xb3c32ed7,0xa248326d,0xb3c32248,0x315f301d,0xa8b2b33b,0xaed733ea,
  0x33eaa248,0xb3882bc6,0x32ddaed7,0xb1ed30c4,0xb2dd2248,0x2248b2dd,0x326d333b,0xb388a8b2,0x30c4a248,0x333b33c3,0xabc62ed7,0xb3feb26d,
  0xabc62248,0xb1edb01d,0xb3eab33b,0xb33bb3ea,0xb26d31ed,0xb33b32dd,0xb3c33388,0xb3fe33ea,0xb3c331ed,0xb1ed33c3,0x28b22d64,0x333bb0c4,
  0xb3ea31ed,0x2d64301d,0x32ddb388,0xb15fa8b2,0xb2dd31ed,0x33feabc6,0xb26dad64,0x2d64326d,0xb0c431ed,0x2ed7b2dd,0xabc63388,0x2248b3ea,
  0xabc631ed,0xb15fb3c3,0x33ea2d64,0xaed730c4,0x28b231ed,0xb388b01d,0xb01db388,0x31ed28b2,0x301d31ed,0xa2482bc6,0xb0c4ad64,0xb388b26d,
  0xb3ea33fe,0xb38833c3,0xb2dd333b,0xb1ed326d,0x32ddb3fe,0x2248b01d,0xb26d2ed7,0xb38833ea,0xb0c433fe,0x333babc6,0x2bc6b33b,0xb3fe30c4,
  0x2bc6b3fe,0xb1ed32dd,0x33eaaed7,0xb33ba8b2,0x28b233fe,0xad64b3c3,0x301d333b,0xb15fb26d,0xb01db3fe,0x33fe301d,0xb0c42ed7,0xad64b3ea,
  0x326d33fe,0xaed72bc6,0xb3c3b33b,0x2248b0c4,0xb3c3b3fe,0xb15fb2dd,0xa8b2aed7,0x2ed728b2,0x29ed29ed,0x29ed29ed,0x29ed29ed,0x29ed29ed,
  0x2bc32a6d,0x2add2bea,0x23c628c4,0xa81da0b2,0x2bc32add,0xa3c6281d,0xabc3aadd,0x23c6a81d,0x29ed2b3b,0xabfea564,0x295fa6d7,0x1a482b88,
  0x25642b88,0xa564ab88,0x25642b88,0xa564ab88,0xa0b22bc3,0x2a6daadd,0xabea23c6,0x28c4281d,0xa8c42bea,0x2a6da0b2,0x28c4abea,0xaa6d20b2,
  0xab3b2bfe,0xa564295f,0x26d79a48,0x2b88a9ed,0x29ed29ed,0x29ed29ed,0x29ed29ed,0x29ed29ed,0xabc3aa6d,0xaaddabea,0xa3c6a8c4,0x281d20b2,
  0x2bc32add,0xa3c6281d,0xabc3aadd,0x23c6a81d,0xa9edab3b,0x2bfe2564,0xa95f26d7,0x9a48ab88,0x25642b88,0xa564ab88,0x25642b88,0xa564ab88,
  0x20b2abc3,0xaa6d2add,0x2beaa3c6,0xa8c4a81d,0xa8c42bea,0x2a6da0b2,0x28c4abea,0xaa6d20b2,0x2b3babfe,0x2564a95f,0xa6d71a48,0xab8829ed,
  0x295f295f,0x295f295f,0x295f295f,0x295f295f,0x23c628c4,0xa81da0b2,0xabc3aa6d,0xaaddabea,0xa3c6281d,0xabc3aadd,0x23c6a81d,0x2bc32add,
  0xa95f26d7,0x9a48ab88,0x29ed2b3b,0xabfea564,0xab882564,0x2b88a564,0xab882564,0x2b88a564,0xabea23c6,0x28c4281d,0x20b2abc3,0xaa6d2add,
  0xaa6d20b2,0xa8c42bea,0x2a6da0b2,0x28c4abea,0xa6d71a48,0xab8829ed,0xab3b2bfe,0xa564295f,0x295f295f,0x295f295f,0x295f295f,0x295f295f,
  0xa3c6a8c4,0x281d20b2,0x2bc32a6d,0x2add2bea,0xa3c6281d,0xabc3aadd,0x23c6a81d,0x2bc32add,0x295fa6d7,0x1a482b88,0xa9edab3b,0x2bfe2564,
  0xab882564,0x2b88a564,0xab882564,0x2b88a564,0x2beaa3c6,0xa8c4a81d,0xa0b22bc3,0x2a6daadd,0xaa6d20b2,0xa8c42bea,0x2a6da0b2,0x28c4abea,
  0x26d79a48,0x2b88a9ed,0x2b3babfe,0x2564a95f,0xabfe2bfe,0xabfe2bfe,0xabfe2bfe,0xabfe2bfe,0xaadd2bea,0xa3c628c4,0x281da0b2,0x2bc3aa6d,
  0xa81d2bc3,0x2adda3c6,0x281dabc3,0xaadd23c6,0x9a482b88,0x29edab3b,0xabfe2564,0x295f26d7,0x26d72b3b,0xa6d7ab3b,0x26d72b3b,0xa6d7ab3b,
  0x2a6d2add,0xabeaa3c6,0x28c4a81d,0x20b22bc3,0x2bea2a6d,0xa0b228c4,0xabeaaa6d,0x20b2a8c4,0x2b8829ed,0x2b3b2bfe,0x2564295f,0xa6d79a48,
  0xabfe2bfe,0xabfe2bfe,0xabfe2bfe,0xabfe2bfe,0x2addabea,0x23c6a8c4,0xa81d20b2,0xabc32a6d,0xa81d2bc3,0x2adda3c6,0x281dabc3,0xaadd23c6,
  0x1a48ab88,0xa9ed2b3b,0x2bfea564,0xa95fa6d7,0x26d72b3b,0xa6d7ab3b,0x26d72b3b,0xa6d7ab3b,0xaa6daadd,0x2bea23c6,0xa8c4281d,0xa0b2abc3,
  0x2bea2a6d,0xa0b228c4,0xabeaaa6d,0x20b2a8c4,0xab88a9ed,0xab3babfe,0xa564a95f,0x26d71a48,0x1a489a48,0x1a489a48,0x1a489a48,0x1a489a48,
  0x281da0b2,0x2bc3aa6d,0x2addabea,0x23c6a8c4,0x2adda3c6,0x281dabc3,0xaadd23c6,0xa81d2bc3,0x2bfea564,0xa95fa6d7,0x9a482b88,0x29edab3b,
  0x2b3ba6d7,0xab3b26d7,0x2b3ba6d7,0xab3b26d7,0x28c4a81d,0x20b22bc3,0xaa6daadd,0x2bea23c6,0x20b2a8c4,0x2bea2a6d,0xa0b228c4,0xabeaaa6d,
  0xa564a95f,0x26d71a48,0x2b8829ed,0x2b3b2bfe,0x1a489a48,0x1a489a48,0x1a489a48,0x1a489a48,0xa81d20b2,0xabc32a6d,0xaadd2bea,0xa3c628c4,
  0x2adda3c6,0x281dabc3,0xaadd23c6,0xa81d2bc3,0xabfe2564,0x295f26d7,0x1a48ab88,0xa9ed2b3b,0x2b3ba6d7,0xab3b26d7,0x2b3ba6d7,0xab3b26d7,
  0xa8c4281d,0xa0b2abc3,0x2a6d2add,0xabeaa3c6,0x20b2a8c4,0x2bea2a6d,0xa0b228c4,0xabeaaa6d,0x2564295f,0xa6d79a48,0xab88a9ed,0xab3babfe,
  0xa95fa95f,0xa95fa95f,0xa95fa95f,0xa95fa95f,0xa3c6a8c4,0x281d20b2,0x2bc32a6d,0x2add2bea,0x23c6a81d,0x2bc32add,0xa3c6281d,0xabc3aadd,
  0x295fa6d7,0x1a482b88,0xa9edab3b,0x2bfe2564,0x2b88a564,0xab882564,0x2b88a564,0xab882564,0x2beaa3c6,0xa8c4a81d,0xa0b22bc3,0x2a6daadd,
  0x2a6da0b2,0x28c4abea,0xaa6d20b2,0xa8c42bea,0x26d79a48,0x2b88a9ed,0x2b3babfe,0x2564a95f,0xa95fa95f,0xa95fa95f,0xa95fa95f,0xa95fa95f,
  0x23c628c4,0xa81da0b2,0xabc3aa6d,0xaaddabea,0x23c6a81d,0x2bc32add,0xa3c6281d,0xabc3aadd,0xa95f26d7,0x9a48ab88,0x29ed2b3b,0xabfea564,
  0x2b88a564,0xab882564,0x2b88a564,0xab882564,0xabea23c6,0x28c4281d,0x20b2abc3,0xaa6d2add,0x2a6da0b2,0x28c4abea,0xaa6d20b2,0xa8c42bea,
  0xa6d71a48,0xab8829ed,0xab3b2bfe,0xa564295f,0x29ed29ed,0x29ed29ed,0x29ed29ed,0x29ed29ed,0x2bc32a6d,0x2add2bea,0x23c628c4,0xa81da0b2,
  0x2bc32add,0xa3c6281d,0xabc3aadd,0x23c6a81d,0x29ed2b3b,0xabfea564,0x295fa6d7,0x1a482b88,0x25642b88,0xa564ab88,0x25642b88,0xa564ab88,
  0xa0b22bc3,0x2a6daadd,0xabea23c6,0x28c4281d,0xa8c42bea,0x2a6da0b2,0x28c4abea,0xaa6d20b2,0xab3b2bfe,0xa564295f,0x26d79a48,0x2b88a9ed,
  0x29ed29ed,0x29ed29ed,0x29ed29ed,0x29ed29ed,0xabc3aa6d,0xaaddabea,0xa3c6a8c4,0x281d20b2,0x2bc32add,0xa3c6281d,0xabc3aadd,0x23c6a81d,
  0xa9edab3b,0x2bfe2564,0xa95f26d7,0x9a48ab88,0x25642b88,0xa564ab88,0x25642b88,0xa564ab88,0x20b2abc3,0xaa6d2add,0x2beaa3c6,0xa8c4a81d,
  0xa8c42bea,0x2a6da0b2,0x28c4abea,0xaa6d20b2,0x2b3babfe,0x2564a95f,0xa6d71a48,0xab8829ed,0x9a481a48,0x9a481a48,0x9a481a48,0x9a481a48,
  0xa81d20b2,0xabc32a6d,0xaadd2bea,0xa3c628c4,0xaadd23c6,0xa81d2bc3,0x2adda3c6,0x281dabc3,0xabfe2564,0x295f26d7,0x1a48ab88,0xa9ed2b3b,
  0xab3b26d7,0x2b3ba6d7,0xab3b26d7,0x2b3ba6d7,0xa8c4281d,0xa0b2abc3,0x2a6d2add,0xabeaa3c6,0xa0b228c4,0xabeaaa6d,0x20b2a8c4,0x2bea2a6d,
  0x2564295f,0xa6d79a48,0xab88a9ed,0xab3babfe,0x9a481a48,0x9a481a48,0x9a481a48,0x9a481a48,0x281da0b2,0x2bc3aa6d,0x2addabea,0x23c6a8c4,
  0xaadd23c6,0xa81d2bc3,0x2adda3c6,0x281dabc3,0x2bfea564,0xa95fa6d7,0x9a482b88,0x29edab3b,0xab3b26d7,0x2b3ba6d7,0xab3b26d7,0x2b3ba6d7,
  0x28c4a81d,0x20b22bc3,0xaa6daadd,0x2bea23c6,0xa0b228c4,0xabeaaa6d,0x20b2a8c4,0x2bea2a6d,0xa564a95f,0x26d71a48,0x2b8829ed,0x2b3b2bfe,
  0xabfe2bfe,0xabfe2bfe,0xabfe2bfe,0xabfe2bfe,0xaadd2bea,0xa3c628c4,0x281da0b2,0x2bc3aa6d,0xa81d2bc3,0x2adda3c6,0x281dabc3,0xaadd23c6,
  0x9a482b88,0x29edab3b,0xabfe2564,0x295f26d7,0x26d72b3b,0xa6d7ab3b,0x26d72b3b,0xa6d7ab3b,0x2a6d2add,0xabeaa3c6,0x28c4a81d,0x20b22bc3,
  0x2bea2a6d,0xa0b228c4,0xabeaaa6d,0x20b2a8c4,0x2b8829ed,0x2b3b2bfe,0x2564295f,0xa6d79a48,0xabfe2bfe,0xabfe2bfe,0xabfe2bfe,0xabfe2bfe,
  0x2addabea,0x23c6a8c4,0xa81d20b2,0xabc32a6d,0xa81d2bc3,0x2adda3c6,0x281dabc3,0xaadd23c6,0x1a48ab88,0xa9ed2b3b,0x2bfea564,0xa95fa6d7,
  0x26d72b3b,0xa6d7ab3b,0x26d72b3b,0xa6d7ab3b,0xaa6daadd,0x2bea23c6,0xa8c4281d,0xa0b2abc3,0x2bea2a6d,0xa0b228c4,0xabeaaa6d,0x20b2a8c4,
  0xab88a9ed,0xab3babfe,0xa564a95f,0x26d71a48,0x3bfb3bff,0x3be53bf2,0x3bbf3bd4,0x3b873ba5,0x3bd03bfb,0x3b013b7c,0x399d3a60,0x378538bc,
  0x35173b52,0xbbc9b7c8,0xb074ba9b,0x3bfe391b,0x319e3b27,0xbbf3b979,0x363cb80a,0x3a2d3bc5,0xba093986,0x3a7eb8f8,0xbae5385f,0x3b3db77a,
  0xbabd393c,0x3bb0b699,0xbc00305b,0x3ba730d7,0xbb2a35c8,0xb8353bb2,0x3a64b1e8,0x3962bbf7,0xba90350b,0xba413bff,0x3602340e,0x3bf6bad8,
  0xac6aa5e4,0xb122af59,0xb402b294,0xb56ab4b7,0xb2deac9c,0xb7bdb5a5,0xb9b3b8d6,0xbb10ba73,0xbb96b676,0xb359bafe,0x3bec3884,0x2a163a29,
  0xbbe0b72c,0x2f27b9d6,0x3b5e3ae8,0xb91633a2,0xb941b9c9,0x38ad3a45,0xb80fbab3,0x36d23b13,0xb850ba0d,0x346f3b4a,0x1fdbbbed,0xb4ab3be8,
  0x3721bb76,0xbace3463,0xb8d13bdd,0x39ebadfb,0x3894bb98,0xb8fd281f,0xbb6a3bbd,0x2e2d3825,0x3b3f3b65,0x3ae83b16,0x3a813ab6,0x3a0d3a49,
  0x3263356a,0xad972b43,0xb5dfb359,0xb8eeb7f3,0xa9b139aa,0xbbedba25,0x3340b889,0x3b983afb,0xbaa2aa16,0xb4cfbb8e,0x3c0038ad,0xb44b38e5,
  0xbb853625,0x3bbdb4c3,0xbbe432ad,0x3bfbaf8b,0xbaacb6d2,0x39243954,0xb65fbace,0x2fbd3bb8,0xb9661648,0xba603bf8,0x383a31cf,0x3b27bbb3,
  0x3219b9eb,0xbb1836f4,0xb9903be5,0x37dd3010,0xb6c6b61a,0xb80ab76f,0xb8a8b85a,0xb93cb8f3,0xbbd7bb87,0xbbf8bbfd,0xbb71bbc9,0xba4dbaf1,
  0xbbfeb9a6,0x305bb91f,0x3bcb3a97,0xb50b37d2,0xb87abbfe,0x3ba13546,0x24523a7e,0xbbb5ba54,0xb576bb63,0x340e3ba3,0xb13bbbd3,0x2c9c3bf2,
  0x386abb3d,0xba2139f8,0x3b57b835,0xbbf13432,0x39e7bc00,0xb8d6adc9,0xbacb3bde,0x372c3457,0x3bdab962,0x3764bb35,0xb9c03122,0xbaf73bef,
  0x398b39cd,0x38fd3946,0x386538b2,0x37853815,0xba85b9c9,0xbb92bb1e,0xbbfebbdd,0xbbc2bbf5,0xb66b3682,0xbb01bb94,0x387fb371,0x3a2d3beb,
  0xbac7bb76,0x3a00ad33,0x36bb3bd4,0xbbeab79b,0xbc0026ad,0x3bf32c38,0xbbd6b109,0x3ba733eb,0x3153bbff,0xb70a3b9e,0x396bba9b,0xbade390c,
  0xb5d4b5bc,0xbbb03b2c,0x32013830,0x3bf6ba67,0x3bccbb52,0x2c06b92e,0xbb83385f,0xb8c73bab,0xb9c5b982,0xba41ba04,0xbab0ba7a,0xbb10bae1,
  0xb8a3b986,0xb52fb74e,0xa94db1e8,0x33d32e91,0xbb54bb4f,0x37bdb523,0x3a9e3bc8,0xb916308d,0x3840b5c8,0x394a3bf9,0xbb42b294,0xb0a6bb0a,
  0x251bbbff,0xaf273bfc,0x327cbbe6,0xb4ab3bc0,0x3be325e4,0xbb2fb4e7,0x39e33884,0xb81aba35,0x3b73bb78,0xb46fb715,0xbbdc3ad1,0x2e2d38cc,
  0x33283676,0x3bfcba19,0x3581bab3,0xba6b3493,0x363136dd,0x34cf3581,0x32c6341a,0x2fbd3153,0xbae1bb65,0xb970ba39,0xb715b889,0xb16cb4f3,
  0xb9a12a7a,0xb924bbfe,0x3a933042,0x37dd3bcc,0x308db9aa,0x3b453b07,0xb94632ad,0xb845bbfa,0xbb68b55e,0x3b1836bb,0xbabab805,0x3a4d38a3,
  0x3bc0b625,0xbbfe2ec3,0x3b9431cf,0xba89b742,0x9cb6b95d,0xbbf8396b,0xb1b63a5c,0x3bb5b840,0x38cc9648,0x3b81bbac,0xac38b85a,0xbbce3933,
  0xbb60bb3a,0xbba1bb83,0xbbd2bbbc,0xbbf1bbe3,0x3815361a,0x39df3907,0x3b2c3a97,0x3be23b9c,0xb9afbbfd,0x3a21294d,0x388e3bee,0xbaf7b328,
  0x3beb39a6,0xb6af37a6,0xba04bbd3,0x3ac42d00,0x360ebb89,0xb7643b42,0x3855baeb,0xb8ee3a85,0x33eb3b63,0x28e8bbf5,0xb5233bde,0x389ebb21,
  0x3c00b9f0,0x2d97b9e3,0xbbdf38db,0xb44b3ac7,0xba673c00,0x358d3487,0x3bfcbab6,0x330fba15,0x3b7a3bf1,0x394a3a93,0x33893764,0xb3d39cb6,
  0x3afb3be2,0x35eb3946,0xb4c328e8,0xbaa9b8cc,0x27763af7,0xbb2fbaba,0x3a76ad97,0x30a63b60,0xaf8b3ac4,0xb994bb94,0x3bf8358d,0xb8743815,
  0xbb4c38ee,0x3bfcb1b6,0xbad5b4cf,0x381a39af,0xbbb3389e,0x3b592c38,0xb76fb970,0xb24b3beb,0xb9d2344b,0xbb923bd2,0xb0f03924,0x3a6bb60e,
  0xb8f3330f,0xbc003b2c,0xb91f3b45,0x323233eb,0xb5b1afbd,0xba00b88e,0xbbc6bb18,0xbbc2bc00,0xb7d2b16c,0xbb6fba04,0xbba3bbfe,0xb86fba67,
  0xbbffb7dd,0x370ab855,0x38b73bf8,0xbbeab631,0xbbf2b845,0x39bcb523,0x2dc93b81,0xbaa5bae1,0xb68dba4d,0xac063bdf,0x382abba1,0xbade39a1,
  0xb457ba89,0xb6543bfc,0x3b16b9df,0xbbd8308d,0x397dbbb5,0xb52fb2c6,0xbbe73a21,0xb8c73b68,0x3a49bbce,0x2311b715,0xba2536af,0xbbd93bc0,
  0xb958b785,0xbb81ba9e,0xbbefbbf3,0xba89bb73,0xbbf7bbc2,0xb9b8bb42,0xaf59b70a,0x384a3328,0xbb8bba2d,0x39dfb27c,0x34263bb0,0xbbceb98b,
  0xb4b7bbea,0x3b6c39e3,0xbafe2c06,0x3185ba85,0xaadebba7,0xb6af3bdc,0x3a58ba41,0xbbe2366b,0x3a29bade,0xbc003581,0x3a45352f,0xb2f7bac7,
  0x3b37bbf6,0x28e8b865,0xbaee37bd,0xbac43c00,0x3b13b8c7,0x3b5cbbfe,0x3463b94a,0xb8993153,0xb9f4bb10,0xb58db87f,0x3029af27,0x389e35d4,
  0x2dfbb3d3,0x399936bb,0x3bf23b2f,0x3ac13bcc,0x3552b916,0x39703bd6,0xbbbab46f,0x330fb9c5,0x3ba530a6,0xb5f7396b,0xb7c8bbfc,0x3be138a3,
  0x3bfdb4ab,0xbb45b201,0x38e038fd,0xb16cbb54,0x391b381a,0xa17fbb83,0xb8f83b92,0x3bcfb840,0x36e82e2d,0x3bfebab0,0x37febb01,0xb845251b,
  0xb77a3a6b,0x3648294d,0x3bb2ba00,0x3a8cbbe3,0xb742b93c,0x2311b340,0x37a6340e,0x3aa93966,0x3b963a4d,0x3b7f3c00,0x380f3a21,0xb0be3219,
  0x3933b50b,0x35eb3be4,0xbbf5b8d6,0x3874b6c6,0x39413bb5,0xbbffb65f,0x38d1b764,0x33ba3bd7,0x3b9c2c9c,0xb994b83a,0x34873ae8,0x324bbbfe,
  0xb7213bf1,0x3b47b990,0xbbbf2d97,0x38c1387a,0x2d00372c,0x3b59b8a8,0x3a39bbed,0xb232b576,0xbbfb3af7,0xb9743b71,0x307434cf,0x3adbb86a,
  0x3b213a0d,0x3c003bcb,0x3b073bbd,0x386f39e7,0x351738ee,0xb599a452,0xbae5b924,0xbbe9bbda,0x3a153b98,0xbb6fb13b,0x2ec3ba60,0x3aa53b3f,
  0xba09344b,0xa884bb57,0x3a643b18,0xbbc3b263,0xb4f33bfb,0x39bcbacb,0xbbac380a,0x3bd8a9b1,0xbb2aafbd,0x36a439c0,0x3402bbf8,0xba6f3aa2,
  0xbbfa3b27,0xb6543a81,0x3907b05b,0x3bd9bb85,0x2c6ab7dd,0xb9da35df,0xbbec3ba1,0xb8203aac,0x3bf53b87,0x3b6c3bec,0x392e3a7e,0x32f73721,
  0xb9e7b785,0xbbfcbb5e,0xba81bbb0,0xb43eb894,0x379b3bfe,0xbc00b80f,0x374eb835,0x38993bfb,0xbb3fba2d,0x3b329fdb,0xb3403a41,0xb8eabbd0,
  0xb90c3b3d,0x3b5cb8d1,0xbbf93122,0x3ac13517,0x29b1bba7,0xb94f3b6a,0x3be4b7bd,0xbaf4b19e,0xbbab3962,0xb9993bbf,0x34e73359,0x3be1ba09,
  0x3b85bbf6,0x353ab99d,0xb83a2f27,0xbbf03abd,0x2e91356a,0xb5f7b074,0xba19b8ad,0xbbcfbb2a,0xb966bb10,0xaba7b63c,0x38a8346f,0x3bb73a90,
  0xbb0aaa16,0xa17fbae5,0x3b1e3ace,0xba8c2c6a,0x36c6b916,0x36ff3c00,0xbbcbb8fd,0x3a50b2de,0xba35b6d2,0x36483a64,0x2d33bbe5,0xb84a3b96,
  0x3bfeb4ab,0xb9fcb602,0x313b3b01,0x37e8bbe0,0x3493b9eb,0xb9b83402,0xbb9e3bc9,0xb1853941,0x35762e2d,0x3b90b9b3,0x3acbbbf3,0x2fefb850,
  0x3a543bcf,0x2884374e,0xb9f8b648,0xbbe9bbab,0x398b3bb7,0xb4db3340,0xbbdcb9fc,0xb911bb85,0xb4323a8c,0xb6a4bbf9,0x3b3539b8,0xbbc3ae91,
  0xb66b3a50,0xad65bbe4,0x38653b90,0xbb0db966,0xbbef384a,0x39da34e7,0x2b43bb6c,0xba6f3b0a,0xbc0037e8,0x3759383a,0x387fbbfc,0xbbf636c6,
  0xb7f33185,0xbb7f3a19,0xbb8e3c00,0xb8203a35,0xb5d42fef,0xba1d38a8,0xbbd63b32,0xbba93bfe,0xb8e5b2f7,0xbbffbb1e,0xb954bb5c,0x30beb493,
  0xb9c5b43e,0xbb9fbbcb,0xb201b94f,0x3a313576,0xbbb8b899,0x3b47ad33,0xb6f43999,0xb3babbf5,0xbb54b8ea,0x3bf9313b,0xbab0353a,0x3790b9e7,
  0xb010bac1,0xb9743b9e,0x3bfdb5f7,0xb8c1b79b,0x251bbaf4,0xbb1b3acb,0x3a9e2ba7,0x2e5fbb3f,0x3af1bbe1,0x3599b92e,0xb546a17f,0xbadb390c,
  0x3b73bbf0,0x3929ba81,0x327cb6ff,0xb49f29b1,0xb825baa9,0x353aaec3,0x3b7c3994,0x3af43bfa,0x360eb0be,0x3bf43a64,0x388e3b47,0xb7372c6a,
  0x38bcb874,0x2ba73bac,0xb979bb59,0x3bf03742,0x3c0033ba,0xbb043402,0x3855b974,0xacce3b96,0x3bc5b24b,0xb6ffb907,0xb6993c00,0x3bb7b933,
  0x363138c1,0x3902bbec,0xbbdf3599,0x34ff3941,0x30d73232,0x39fcb7a6,0x3bffbb6f,0x3a50bb9c,0xb9a13adb,0xb47b380f,0x32c62884,0x3937b721,
  0x3ad8386f,0x3b903bf5,0x35a539bc,0xb7e8ad00,0x3b683be9,0x2ef538d1,0xba93b6a4,0xbb24bbfb,0x3a733aa5,0xbbfcb487,0x39d6b654,0xafef3b21,
  0x1cb63bc3,0xb7b2bbbf,0x3aba39da,0xbbfab517,0xb3a23bd8,0x3b32ba39,0xbb4a2311,0x343e3a15,0xbb603a6f,0x3a3d3074,0x31b6bb7f,0xbb9a3a09,
  0xbbe83bd9,0xb94f3b07,0xa81f35eb,0x38eab4f3,0xb9af3820,0xbbae3ae5,0xbbd23bff,0xba113b2a,0x319e389e,0xb929b426,0xbc00bb45,0xb911bb37,
  0xbbffbac1,0xb805bafe,0x382a217f,0x3bfd3b13,0xbabd330f,0x34dbba58,0x36023bfe,0xbb0db9f4,0xb68dbbe1,0x3a5c3a45,0xbbe7b648,0x3b89adfb,
  0xba90b16c,0x2d653aee,0x39b3bb81,0xbbf63552,0x397dbbcf,0xbbbc3463,0x338939b8,0x39f0bba5,0x32deb845,0xb7593029,0xbb5e39df,0xbba93bfd,
  0x3b7aba8c,0x3beebbf2,0x3a76bb6c,0x36ddb91b,0xbbe0ba89,0xba1dbbba,0x1fdbb6af,0x3a3136e8,0xa776b84a,0x3aeb37c8,0x3ad53c00,0xaa7a377a,
  0xb850bbce,0x3b9f38e0,0xbb6a28e8,0x3790b958,0x3b4cb185,0xb8db38f8,0x30f0bb5c,0x355e3bf7,0x3894bbe2,0xbbf937fe,0x399d358d,0x2e5fbb8b,
  0x39d232f7,0x341abbb2,0xbbc63999,0x395d34b7,0x3bd0bac4,0x3b1bbbef,0x363cb970,0xb49faade,0xb5b13899,0x30422f59,0x38b7b5f7,0x3b3aba29,
  0x3219b3d3,0x3b0438b7,0x3b713bfc,0x34ff397d,0x36e83aa9,0xb8b2adc9,0xbbefbb59,0xb5bcba49,0x3bd730a6,0xb902382a,0xa452bb92,0x39373b7a,
  0xb9583874,0x3371bb16,0x34263c00,0xb982bafb,0x387a381a,0x347bbbe7,0xbb573a00,0x3b242776,0xbb8b324b,0x31093a25,0x3a58bb6f,0xbb4f2f8b,
  0xb86a3a6b,0x2ef53389,0x39c0b70a,0x3bfabb4c,0xaadeb232,0xb83034c3,0xbaee39bc,0xbbff3bb3,0x3bda3bc2,0x37b23a76,0xb5df2c06,0xbb9ab9d2,
  0xbb37b86f,0xba7abbf8,0x3029b654,0x3b7838f3,0x32633bea,0xba3dbad5,0x3c00352f,0xba1135b1,0xb9f4baa5,0x3bc8376f,0xbbba2311,0x39cdb7d2,
  0xbaa23ade,0x3baeb0f0,0xb65fb94a,0xb7373bff,0x3552bbd8,0xbbe6391f,0x38e035eb,0x3682bbf2,0xbaac38c7,0xbbf43bc6,0xb9903b2f,0xacce368d,
  0x3bfdbbd9,0x3ad1bba3,0x37feb994,0x26adb457,0x38a33b9a,0xb8dba452,0xbb83bbae,0x2a7ab86a,0x37423b78,0xbab6b426,0xb907bbe6,0x39aa2ade,
  0xb8403a11,0x341abb57,0x294d3bf4,0xb55ebbda,0xb93339cd,0x3889ba58,0xb7a63ad1,0x3625bb37,0xbbe33737,0x304239c0,0x3b42bb04,0xb95db263,
  0xbb9c3682,0xb2ad3aee,0x3bf5b8b2,0x1648b9f4,0xb3282cce,0xb80535df,0xb9e33902,0xbb3a3aa2,0xad0026ad,0xb1cf3029,0xb4873371,0xb61a3552,
  0xba85b4ff,0xba5cbc00,0x3581b47b,0x3bfd3aac,0xbb21b5bc,0xb85abbba,0x3a393109,0x39a63bfd,0xbac7b937,0x3bbc365f,0xbbfeaef5,0x3b89b219,
  0xba15b982,0x3a9738e0,0xbb07b830,0x3b6336e8,0x3153bb24,0xbbee3990,0x36bb37b2,0x39f0bbd7,0x34f3bb4f,0xbbd337fe,0xaec33a7a,0x3c00b958,
  0x3bccbbfa,0x3aebbb71,0x396bba3d,0x36ddb87a,0x3bfabbff,0x3bdebbef,0x3bacbbc8,0x3b65bb8b,0x3bc03911,0x38303b6a,0xb946ad65,0xbb4fbbd0,
  0x3a353bfd,0xb85f30f0,0xbb1ebbbc,0x35c8b5b1,0x38cc3b0d,0xba7ab99d,0x3b943759,0xbbffb19e,0xb4933b89,0x31e8bbc6,0xad333bee,0xa5e4bbff,
  0xb8153bf6,0x3bc8b63c,0xac38ba1d,0xbb783abd,0xbbf539f0,0x329438b7,0x3b9ebaeb,0xb676b68d,0xbbeb3ba9,0xbbe63c00,0xbb2c3b9f,0xb9cd3a90,
  0xb79b36dd,0xb884382a,0xb92e38db,0xb9c9397d,0x33eb3a31,0xbad1b602,0xba04bbf9,0x3682b2de,0xb90c2a7a,0xbab3bbe7,0x374eb41a,0x3b763b7a,
  0xba673790,0x38b2b9b3,0xb5233b1b,0x26adbbe0,0xbbabb55e,0x3bdd3389,0xbbf9b042,0x3bff2776,0xbae12e5f,0xb3713b5e,0x3bfcb929,0xb5bcb850,
  0xae91b95d,0xbbd43a76,0x34e73805,0x3b52bb4c,0x308db49f,0xb1091fdb,0xb71534db,0xb9823894,0x3b0abb3a,0x3a9bbad5,0x3a19ba5c,0x3986b9d2,
  0x2f8bb7e8,0x3bde3979,0x376f3b32,0xb9aab0d7,0x3bb83b24,0xb1223855,0xbbfdba3d,0xaa16b9a1,0x3bb3afef,0xbab63699,0x391fb94f,0xb6253ad8,
  0x30103bfa,0xb359bbdf,0x35463bae,0xb6d2bb68,0x38f3343e,0x3889bbff,0xbba3353a,0x96483a73,0xbaf13b9a,0x38ad32c6,0x39f8bbf4,0xb9eb9cb6,
  0xb7d238ea,0xb2ad35a5,0x2dc92ba7,0x361ab3a2,0xba543a11,0xbace3a93,0xbb353b04,0xbb873b60,0x3bf23af4,0x31cf39d6,0xbb16b6ff,0xb9a6bbe8,
  0xb4323737,0xbbe5baba,0x2b43b902,0x3bfe39af,0x34573bf0,0xb85abb4a,0x3a2539fc,0xbb63b825,0xbbef2cce,0x3bc9b1b6,0xbb8e347b,0x3b3db60e,
  0xba493bb7,0x3a97a81f,0x34c3bb90,0xbc0038bc,0xb7f3b4ff,0xba7e3bd2,0x39542ef5,0x3962bc00,0xbafb3a50,0xbbd33b7c,0xbbf83bfc,0xbb653bc5,
  0x38e5b937,0x3835b88e,0x36f4b7b2,0x356ab631,0xbb13bbe9,0x31e8b6f4,0x3bf239da,0x36763af1,0x3be83911,0x340e3ab0,0xbb7cb759,0xb72cbb73,
  0x2dfbbbc3,0x32943bfd,0xb7c8bb7f,0x39c93a54,0x38253b0d,0xb8d6ba9e,0x39793a1d,0xba0db98b,0x3ba5ba6f,0xb884b546,0xb8f83bff,0x3b76b432,
  0xb8bc3bf6,0x3ae8b27c,0x3699bb9f,0xbb98366b,0x391bb820,0x3ab3b9f8,0x3bb2bb47,0x3bffbbef,0xbbc53ba9,0xbbed3bdc,0xbbff3bf9,0xbbfb3c00,
  0x377ab0be,0x3bdd3b35,0x2f593974,0xbb52b7f3,0x30d73a31,0xbbbdb865,0xb5a5bb1b,0x3b2735d4,0x3bf733ba,0xbbd42b43,0x3afeb599,0xb98638e5,
  0xbad83790,0x3a60b87f,0xb9d63929,0x393cb9c5,0x34b738c1,0x3a9bbb8e,0xba45a884,0xb5c83bb8,0xba732e5f,0xb80a3bd6,0x3b4ab4db,0x350bbb54,
  0xba293adb,0xb85f3954,0xb46336a4,0x25e43010,0x33a2b49f,0x305bb201,0x281fad65,0xac9c251b,0x3f803f80,0x3f803f80,0x3f803f80,0x3f803f80,
  0x3f803f80,0x3f803f80,0x3f803f80,0x3f803f80,0x3f803f80,0x3f803f80,0x3f803f80,0x3f803f80,0x3f803f80,0x3f803f80,0x3f803f80,0x3f803f80,
  0x3f803f80,0x3f803f80,0x3f803f80,0x3f803f80,0x3f803f80,0x3f803f80,0x3f803f80,0x3f803f80,0x3f803f80,0x3f803f80,0x3f803f80,0x3f803f80,
  0x3f803f80,0x3f803f80,0x3f803f80,0x3f803f80,0x3f803f80,0x3f803f80,0x3f803f80,0x3f803f80,0x3f803f80,0x3f803f80,0x3f803f80,0x3f803f80,
  0x3f803f80,0x3f803f80,0x3f803f80,0x3f803f80,0x3f803f80,0x3f803f80,0x3f803f80,0x3f803f80,0x3f803f80,0x3f803f80,0x3f803f80,0x3f803f80,
  0x3f803f80,0x3f803f80,0x3f803f80,0x3f803f80,0x3f803f80,0x3f803f80,0x3f803f80,0x3f803f80,0x3f803f80,0x3f803f80,0x3f803f80,0x3f803f80,
  0x3f803f80,0x3f803f80,0x3f803f80,0x3f803f80,0x3f803f80,0x3f803f80,0x3f803f80,0x3f803f80,0x3f803f80,0x3f803f80,0x3f803f80,0x3f803f80,
  0x3f803f80,0x3f803f80,0x3f803f80,0x3f803f80,0x3f803f80,0x3f803f80,0x3f803f80,0x3f803f80,0x3f803f80,0x3f803f80,0x3f803f80,0x3f803f80,
  0x3f803f80,0x3f803f80,0x3f803f80,0x3f803f80,0x3f803f80,0x3f803f80,0x3f803f80,0x3f803f80,0x3f803f80,0x3f803f80,0x3f803f80,0x3f803f80,
  0x3f803f80,0x3f803f80,0x3f803f80,0x3f803f80,0x3f803f80,0x3f803f80,0x3f803f80,0x3f803f80,0x3f803f80,0x3f803f80,0x3f803f80,0x3f803f80,
  0x3f803f80,0x3f803f80,0x3f803f80,0x3f803f80,0x3f803f80,0x3f803f80,0x3f803f80,0x3f803f80,0x3f803f80,0x3f803f80,0x3f803f80,0x3f803f80,
  0x3f803f80,0x3f803f80,0x3f803f80,0x3f803f80,0x3f803f80,0x3f803f80,0x3f803f80,0x3f803f80,0x3f803f80,0x3f803f80,0x3f803f80,0x3f803f80,
  0x3f803f80,0x3f803f80,0x3f803f80,0x3f803f80,0x3f803f80,0x3f803f80,0x3f803f80,0x3f803f80,0x3f803f80,0x3f803f80,0x3f803f80,0x3f803f80,
  0x3f803f80,0x3f803f80,0x3f803f80,0x3f803f80,0x3f803f80,0x3f803f80,0x3f803f80,0x3f803f80,0x3f803f80,0x3f803f80,0x3f803f80,0x3f803f80,
  0x3f803f80,0x3f803f80,0x3f803f80,0x3f803f80,0x3f803f80,0x3f803f80,0x3f803f80,0x3f803f80,0x3f803f80,0x3f803f80,0x3f803f80,0x3f803f80,
  0x3f803f80,0x3f803f80,0x3f803f80,0x3f803f80,0x3f803f80,0x3f803f80,0x3f803f80,0x3f803f80,0x3f803f80,0x3f803f80,0x3f803f80,0x3f803f80,
  0x3f803f80,0x3f803f80,0x3f803f80,0x3f803f80,0x3f803f80,0x3f803f80,0x3f803f80,0x3f803f80,0x3f803f80,0x3f803f80,0x3f803f80,0x3f803f80,
  0x3f803f80,0x3f803f80,0x3f803f80,0x3f803f80,0x3f803f80,0x3f803f80,0x3f803f80,0x3f803f80,0x3f803f80,0x3f803f80,0x3f803f80,0x3f803f80,
  0x3f803f80,0x3f803f80,0x3f803f80,0x3f803f80,0x3f803f80,0x3f803f80,0x3f803f80,0x3f803f80,0x3f803f80,0x3f803f80,0x3f803f80,0x3f803f80,
  0x3f803f80,0x3f803f80,0x3f803f80,0x3f803f80,0x3f803f80,0x3f803f80,0x3f803f80,0x3f803f80,0x3f803f80,0x3f803f80,0x3f803f80,0x3f803f80,
  0x3f803f80,0x3f803f80,0x3f803f80,0x3f803f80,0x3f803f80,0x3f803f80,0x3f803f80,0x3f803f80,0x3f803f80,0x3f803f80,0x3f803f80,0x3f803f80,
  0x3f803f80,0x3f803f80,0x3f803f80,0x3f803f80,0x3f803f80,0x3f803f80,0x3f803f80,0x3f803f80,0x3f803f80,0x3f803f80,0x3f803f80,0x3f803f80,
  0x3f803f80,0x3f803f80,0x3f803f80,0x3f803f80,0x3f803f80,0x3f803f80,0x3f803f80,0x3f803f80,0x3f803f80,0x3f803f80,0x3f803f80,0x3f803f80,
  0x3f803f80,0x3f803f80,0x3f803f80,0x3f803f80,0x3f803f80,0x3f803f80,0x3f803f80,0x3f803f80,0x3f803f80,0x3f803f80,0x3f803f80,0x3f803f80,
  0x3f803f80,0x3f803f80,0x3f803f80,0x3f803f80,0x3f803f80,0x3f803f80,0x3f803f80,0x3f803f80,0x3f803f80,0x3f803f80,0x3f803f80,0x3f803f80,
  0x3f803f80,0x3f803f80,0x3f803f80,0x3f803f80,0x3f803f80,0x3f803f80,0x3f803f80,0x3f803f80,0x3f803f80,0x3f803f80,0x3f803f80,0x3f803f80,
  0x3f803f80,0x3f803f80,0x3f803f80,0x3f803f80,0x3f803f80,0x3f803f80,0x3f803f80,0x3f803f80,0x3f803f80,0x3f803f80,0x3f803f80,0x3f803f80,
  0x3f803f80,0x3f803f80,0x3f803f80,0x3f803f80,0x3f803f80,0x3f803f80,0x3f803f80,0x3f803f80,0x3f803f80,0x3f803f80,0x3f803f80,0x3f803f80,
  0x3f803f80,0x3f803f80,0x3f803f80,0x3f803f80,0x3f803f80,0x3f803f80,0x3f803f80,0x3f803f80,0x3f803f80,0x3f803f80,0x3f803f80,0x3f803f80,
  0x3f803f80,0x3f803f80,0x3f803f80,0x3f803f80,0x3f803f80,0x3f803f80,0x3f803f80,0x3f803f80,0x3f803f80,0x3f803f80,0x3f803f80,0x3f803f80,
  0x3f803f80,0x3f803f80,0x3f803f80,0x3f803f80,0x3f803f80,0x3f803f80,0x3f803f80,0x3f803f80,0x3f803f80,0x3f803f80,0x3f803f80,0x3f803f80,
  0x3f803f80,0x3f803f80,0x3f803f80,0x3f803f80,0x3f803f80,0x3f803f80,0x3f803f80,0x3f803f80,0x3f803f80,0x3f803f80,0x3f803f80,0x3f803f80,
  0x3f803f80,0x3f803f80,0x3f803f80,0x3f803f80,0x3f803f80,0x3f803f80,0x3f803f80,0x3f803f80,0x3f803f80,0x3f803f80,0x3f803f80,0x3f803f80,
  0x3f803f80,0x3f803f80,0x3f803f80,0x3f803f80,0x3f803f80,0x3f803f80,0x3f803f80,0x3f803f80,0x3f803f80,0x3f803f80,0x3f803f80,0x3f803f80,
  0x3f803f80,0x3f803f80,0x3f803f80,0x3f803f80,0x3f803f80,0x3f803f80,0x3f803f80,0x3f803f80,0x3f803f80,0x3f803f80,0x3f803f80,0x3f803f80,
  0x3f803f80,0x3f803f80,0x3f803f80,0x3f803f80,0x3f803f80,0x3f803f80,0x3f803f80,0x3f803f80,0x3f803f80,0x3f803f80,0x3f803f80,0x3f803f80,
  0x3f803f80,0x3f803f80,0x3f803f80,0x3f803f80,0x3f803f80,0x3f803f80,0x3f803f80,0x3f803f80,0x3f803f80,0x3f803f80,0x3f803f80,0x3f803f80,
  0x3f803f80,0x3f803f80,0x3f803f80,0x3f803f80,0x3f803f80,0x3f803f80,0x3f803f80,0x3f803f80,0x3f803f80,0x3f803f80,0x3f803f80,0x3f803f80,
  0x3f803f80,0x3f803f80,0x3f803f80,0x3f803f80,0x3f803f80,0x3f803f80,0x3f803f80,0x3f803f80,0x3f803f80,0x3f803f80,0x3f803f80,0x3f803f80,
  0x3f803f80,0x3f803f80,0x3f803f80,0x3f803f80,0x3f803f80,0x3f803f80,0x3f803f80,0x3f803f80,0x3f803f80,0x3f803f80,0x3f803f80,0x3f803f80,
  0x3f803f80,0x3f803f80,0x3f803f80,0x3f803f80,0x3f803f80,0x3f803f80,0x3f803f80,0x3f803f80,0x3f803f80,0x3f803f80,0x3f803f80,0x3f803f80,
  0x3f803f80,0x3f803f80,0x3f803f80,0x3f803f80,0x3f803f80,0x3f803f80,0x3f803f80,0x3f803f80,0x3f803f80,0x3f803f80,0x3f803f80,0x3f803f80,
  0x3f803f80,0x3f803f80,0x3f803f80,0x3f803f80,0x3f803f80,0x3f803f80,0x3f803f80,0x3f803f80,0x3f803f80,0x3f803f80,0x3f803f80,0x3f803f80,
  0x3f803f80,0x3f803f80,0x3f803f80,0x3f803f80,
};

__device__ __align__(128) float    g_part[16][8][2176];
__device__ __align__(128) float    g_kv[16][2176];
__device__ __align__(128) uint4    g_o[16 * 16 * 1024];
__device__ __align__(128) unsigned g_ocnt[16 * 32];
__device__ unsigned g_epoch[128];
#define GSTAMP(role, i) do {} while (0)
#define STAMP(role, i) do {} while (0)
#define PDUMP(role) do {} while (0)
#define PROF_SMEM 0

constexpr int STAGE_BYTES = 57344;
constexpr int OFF_H = 4 * 16384, OFF_VP = 9 * 16384, OFF_SPARE = 10 * 16384;
constexpr int OFF_XT = 172032, XT_STRIDE = 4112;
constexpr int OFF_BAR = 204928, OFF_EPOCH = OFF_BAR + 640, OFF_EX = OFF_BAR + 656, OFF_D = OFF_BAR + 672, OFF_SCALE = OFF_BAR + 704;
constexpr int OFF_F2F = 205824, OFF_F2I = 207872, OFF_F4 = 209920, OFF_ONES = 214016, OFF_KVB = 214016;
constexpr int OFF_STG = 219136, STG_STRIDE = 4352, SMEM_TOTAL = 232192 + PROF_SMEM;
enum { B_FULL1 = 0, B_EMPTY1 = 3, B_Q = 6, B_XRAW = 10, B_XT = 11, B_KV = 12, B_Y = 13, B_PKFREE = 14, B_AFREE = 15,
       B_STG = 18, B_ODONE = 24, B_XFREE = 25, B_FULL2 = 33, B_CONS2 = 49, B_COUNT = 62 };
__host__ __device__ constexpr int bar_count(int i) {
  return i < B_EMPTY1 ? 1 : i < B_Q ? 4 : i == B_XT ? 4 : i == B_KV ? 2 : i == B_Y ? 9 : i == B_PKFREE ? 8
       : (i >= B_AFREE && i < B_STG) ? 16 : i == B_ODONE ? 8 : (i >= B_XFREE && i < B_FULL2) ? 4
       : (i >= B_CONS2 && i <= B_CONS2 + 10) ? 4 : i >= B_CONS2 ? 2 : (i >= B_FULL2 && i < B_FULL2 + 7) ? 2 : 1;
}
__host__ __device__ constexpr uint64_t bar_counts(int r) {
  uint64_t v = 0;
  for (int w = 0; w < 11; w++) v |= (uint64_t)(bar_count(1 + 11 * r + w) - 1) << (4 * w);
  return v;
}
constexpr uint64_t SLOT_A = 0x9245392453924594ull;
constexpr uint64_t SLOT_B = 0x7610876108761032ull;
constexpr int SPIN_LIMIT = 1 << 22;
#define PKV CU_TENSOR_MAP_L2_PROMOTION_L2_128B
#define BPRE B_KV
#define PFD 3
#define PD1 400
#define PD2 100
#define E1C 2
#define OSP 4
#define QPF 4
#define TSPLIT 1
#define OC0 1
#define OC1 1
#define BSPL 4
#define BPACE 600
#define NPOS 0
#define HSTART 1500
#define PACE 1050
#define OC 1

__device__ __forceinline__ uint32_t smem_u32(const void* p) { return (uint32_t)__cvta_generic_to_shared(p); }
__device__ __forceinline__ void wg_fence() { asm volatile("wgmma.fence.sync.aligned;" ::: "memory"); }
__device__ __forceinline__ void wg_commit() { asm volatile("wgmma.commit_group.sync.aligned;" ::: "memory"); }
template <int N> __device__ __forceinline__ void wg_wait() { asm volatile("wgmma.wait_group.sync.aligned %0;" ::"n"(N) : "memory"); }
template <int N> __device__ __forceinline__ void keep(float (&d)[N]) {
#pragma unroll
  for (int i = 0; i < N; i++) asm volatile("" : "+f"(d[i])::"memory");
}
__device__ __forceinline__ uint64_t mkdesc(uint32_t addr, uint32_t lbo, uint32_t sbo, uint32_t swz) {
  uint32_t lo = ((addr & 0x3FFFF) >> 4) | ((lbo >> 4) << 16), hi = (sbo >> 4) | (swz << 30);
  return ((uint64_t)hi << 32) | lo;
}
__device__ __forceinline__ void mbar_init(uint32_t bar, int cnt) { asm volatile("mbarrier.init.shared::cta.b64 [%0], %1;" ::"r"(bar), "r"(cnt)); }
__device__ __forceinline__ void mbar_expect(uint32_t bar, int bytes) { asm volatile("mbarrier.arrive.expect_tx.shared::cta.b64 _, [%0], %1;" ::"r"(bar), "r"(bytes) : "memory"); }
__device__ __forceinline__ void mbar_arrive(uint32_t bar) { asm volatile("mbarrier.arrive.shared::cta.b64 _, [%0];" ::"r"(bar) : "memory"); }
__device__ __forceinline__ void mbar_arrive_cl(uint32_t bar, uint32_t cta) {
  asm volatile("{\n.reg .b32 r;\nmapa.shared::cluster.u32 r, %0, %1;\nmbarrier.arrive.shared::cluster.b64 _, [r];\n}\n" ::"r"(bar), "r"(cta) : "memory");
}
__device__ __forceinline__ void mbar_wait(uint32_t bar, uint32_t parity) {
  asm volatile("{\n.reg .pred p;\n.reg .u32 n;\nmov.u32 n, 0;\n"
               "W_%=:\nmbarrier.try_wait.parity.shared::cta.b64 p, [%0], %1;\n@p bra D_%=;\n"
               "add.u32 n, n, 1;\nsetp.lt.u32 p, n, %2;\n@p bra W_%=;\ntrap;\nD_%=:\n}\n" ::"r"(bar), "r"(parity), "n"(SPIN_LIMIT) : "memory");
}
__device__ __forceinline__ void fence_async() { asm volatile("fence.proxy.async.shared::cta;" ::: "memory"); }
__device__ __forceinline__ void bar_sync(int id) { asm volatile("bar.sync %0, 128;" ::"r"(id) : "memory"); }
__device__ __forceinline__ void tma2d(uint32_t dst, const CUtensorMap* m, int c0, int c1, uint32_t bar) {
  asm volatile("cp.async.bulk.tensor.2d.shared::cluster.global.mbarrier::complete_tx::bytes [%0], [%1, {%3, %4}], [%2];"
               ::"r"(dst), "l"(m), "r"(bar), "r"(c0), "r"(c1) : "memory");
}
__device__ __forceinline__ void tma2d_mc(uint32_t dst, const CUtensorMap* m, int c0, int c1, uint32_t bar) {
  asm volatile("cp.async.bulk.tensor.2d.shared::cluster.global.mbarrier::complete_tx::bytes.multicast::cluster [%0], [%1, {%3, %4}], [%2], %5;"
               ::"r"(dst), "l"(m), "r"(bar), "r"(c0), "r"(c1), "h"((uint16_t)3) : "memory");
}
__device__ __forceinline__ void tma3d(uint32_t dst, const CUtensorMap* m, int c0, int c1, int c2, uint32_t bar) {
  asm volatile("cp.async.bulk.tensor.3d.shared::cluster.global.mbarrier::complete_tx::bytes [%0], [%1, {%3, %4, %5}], [%2];"
               ::"r"(dst), "l"(m), "r"(bar), "r"(c0), "r"(c1), "r"(c2) : "memory");
}
__device__ __forceinline__ void bulk_ld(uint32_t dst, const void* src, int bytes, uint32_t bar) {
  asm volatile("cp.async.bulk.shared::cluster.global.mbarrier::complete_tx::bytes [%0], [%1], %2, [%3];" ::"r"(dst), "l"(src), "r"(bytes), "r"(bar) : "memory");
}
__device__ __forceinline__ void bulk_ld_mc(uint32_t dst, const void* src, int bytes, uint32_t bar) {
  asm volatile("cp.async.bulk.shared::cluster.global.mbarrier::complete_tx::bytes.multicast::cluster [%0], [%1], %2, [%3], %4;"
               ::"r"(dst), "l"(src), "r"(bytes), "r"(bar), "h"((uint16_t)3) : "memory");
}
__device__ __forceinline__ void tma2d_st(const CUtensorMap* m, uint32_t src, int c0, int c1) {
  asm volatile("cp.async.bulk.tensor.2d.global.shared::cta.bulk_group [%0, {%2, %3}], [%1];" ::"l"(m), "r"(src), "r"(c0), "r"(c1) : "memory");
}
__device__ __forceinline__ void pf_l2(const void* p, int bytes) { asm volatile("cp.async.bulk.prefetch.L2.global [%0], %1;" ::"l"(p), "r"(bytes) : "memory"); }
__device__ __forceinline__ void pf_t2d(const CUtensorMap* m, int c0, int c1) {
  asm volatile("cp.async.bulk.prefetch.tensor.2d.L2.global [%0, {%1, %2}];" ::"l"(m), "r"(c0), "r"(c1) : "memory");
}
__device__ __forceinline__ void pf_t3d(const CUtensorMap* m, int c0, int c1, int c2) {
  asm volatile("cp.async.bulk.prefetch.tensor.3d.L2.global [%0, {%1, %2, %3}];" ::"l"(m), "r"(c0), "r"(c1), "r"(c2) : "memory");
}
__device__ __forceinline__ void ldsm4(uint32_t (&r)[4], uint32_t a) {
  asm volatile("ldmatrix.sync.aligned.m8n8.x4.shared.b16 {%0,%1,%2,%3}, [%4];" : "=r"(r[0]), "=r"(r[1]), "=r"(r[2]), "=r"(r[3]) : "r"(a) : "memory");
}
__device__ __forceinline__ void ldsm4t(uint32_t (&r)[4], uint32_t a) {
  asm volatile("ldmatrix.sync.aligned.m8n8.x4.trans.shared.b16 {%0,%1,%2,%3}, [%4];" : "=r"(r[0]), "=r"(r[1]), "=r"(r[2]), "=r"(r[3]) : "r"(a) : "memory");
}
__device__ __forceinline__ void stsm4(uint32_t a, uint32_t r0, uint32_t r1, uint32_t r2, uint32_t r3) {
  asm volatile("stmatrix.sync.aligned.m8n8.x4.shared.b16 [%0], {%1,%2,%3,%4};" ::"r"(a), "r"(r0), "r"(r1), "r"(r2), "r"(r3) : "memory");
}
__device__ __forceinline__ uint32_t pk2(float lo, float hi) { uint32_t r; asm("cvt.rn.bf16x2.f32 %0, %1, %2;" : "=r"(r) : "f"(hi), "f"(lo)); return r; }
__device__ __forceinline__ uint32_t hmul(uint32_t a, uint32_t b) { uint32_t r; asm("mul.rn.bf16x2 %0, %1, %2;" : "=r"(r) : "r"(a), "r"(b)); return r; }
__device__ __forceinline__ uint32_t hadd(uint32_t a, uint32_t b) { uint32_t r; asm("add.rn.bf16x2 %0, %1, %2;" : "=r"(r) : "r"(a), "r"(b)); return r; }
__device__ __forceinline__ uint32_t hmax(uint32_t a, uint32_t b) { uint32_t r; asm("max.bf16x2 %0, %1, %2;" : "=r"(r) : "r"(a), "r"(b)); return r; }
__device__ __forceinline__ uint32_t hmin(uint32_t a, uint32_t b) { uint32_t r; asm("min.bf16x2 %0, %1, %2;" : "=r"(r) : "r"(a), "r"(b)); return r; }
__device__ __forceinline__ uint32_t hmaxabs(uint32_t a, uint32_t b) { uint32_t r; asm("max.xorsign.abs.bf16x2 %0, %1, %2;" : "=r"(r) : "r"(a), "r"(b)); return r; }
__device__ __forceinline__ float ex2(float x) { float r; asm("ex2.approx.ftz.f32 %0, %1;" : "=f"(r) : "f"(x)); return r; }
__device__ __forceinline__ float rcp_fast(float x) { float r; asm("rcp.approx.ftz.f32 %0, %1;" : "=f"(r) : "f"(x)); return r; }
__device__ __forceinline__ uint32_t phi2(float lo, float hi) {
  uint32_t t;
  asm("cvt.rn.relu.bf16x2.f32 %0, %1, %2;" : "=r"(t) : "f"(hi), "f"(lo));
  const uint32_t e = pk2(ex2(lo * 1.4426950408889634f), ex2(hi * 1.4426950408889634f));
  return hadd(hadd(t, hmin(e, 0x3F803F80u)), 0x35863586u);
}
__device__ __forceinline__ bool opaque_true() { uint32_t v; asm volatile("mov.u32 %0, %%nctaid.y;" : "=r"(v)); return v != 0; }
__device__ __forceinline__ int normalise(uint32_t (&v)[32], float fd) {
  const float f0 = fd + __uint_as_float(v[0] << 16);
  uint32_t m[4] = {hmaxabs(__float_as_uint(f0) >> 16, v[0]), v[1], v[2], v[3]};
#pragma unroll
  for (int i = 4; i < 32; i++) m[i & 3] = hmaxabs(m[i & 3], v[i]);
  m[0] = hmaxabs(hmaxabs(m[0], m[1]), hmaxabs(m[2], m[3]));
  const int e = min(max((int)(__reduce_max_sync(~0u, max(m[0] & 0x7FFFu, (m[0] >> 16) & 0x7FFFu)) >> 7), 1), 253);
  if (e > 141) {
#pragma unroll
    for (int i = 0; i < 32; i++) v[i] = hmul(v[i], 0x07000700u);
  }
  const uint32_t sc = (e > 141 ? 255 - e : 142 - e) * 0x00800080u;
#pragma unroll
  for (int i = 0; i < 32; i++) {
    const uint32_t a = hmul(v[i], sc);
    v[i] = (a & 0x0FFF0FFFu) * 7 + a;
  }
  v[0] = __byte_perm(v[0], __half_as_ushort(__float2half_rn(f0 * __uint_as_float((254 - e) << 23))), 0x3254);
  return e;
}
__device__ __forceinline__ void poll_ge(const unsigned* p, unsigned target) {
#pragma unroll 1
  for (int n = 0; n < SPIN_LIMIT; n++) {
    unsigned v;
    asm volatile("ld.relaxed.gpu.global.u32 %0, [%1];" : "=r"(v) : "l"(p) : "memory");
    if ((int)(v - target) >= 0) { asm volatile("fence.acquire.gpu;" ::: "memory"); return; }
  }
  __trap();
}

__device__ __forceinline__ bool elect_one() {
  uint32_t p;
  asm volatile("{\n.reg .pred p;\nelect.sync _|p, 0xffffffff;\nselp.u32 %0, 1, 0, p;\n}\n" : "=r"(p));
  return p;
}
__device__ __forceinline__ uint32_t mapa(uint32_t a, uint32_t cta) { uint32_t r; asm("mapa.shared::cluster.u32 %0, %1, %2;" : "=r"(r) : "r"(a), "r"(cta)); return r; }
__device__ __forceinline__ void st_async(uint32_t a, uint32_t v, uint32_t bar) {
  asm volatile("st.async.weak.shared::cluster.mbarrier::complete_tx::bytes.b32 [%0], %1, [%2];" ::"r"(a), "r"(v), "r"(bar) : "memory");
}
__device__ __forceinline__ void st_async4(uint32_t a, uint32_t x, uint32_t y, uint32_t z, uint32_t w, uint32_t bar) {
  asm volatile("st.async.weak.shared::cluster.mbarrier::complete_tx::bytes.v4.b32 [%0], {%1,%2,%3,%4}, [%5];" ::"r"(a), "r"(x), "r"(y), "r"(z), "r"(w), "r"(bar) : "memory");
}
__device__ __forceinline__ void tma3d_st(const CUtensorMap* m, uint32_t src, int c0, int c1, int c2) {
  asm volatile("cp.async.bulk.tensor.3d.global.shared::cta.bulk_group [%0, {%2, %3, %4}], [%1];" ::"l"(m), "r"(src), "r"(c0), "r"(c1), "r"(c2) : "memory");
}
__device__ __forceinline__ uint4 ld_rlx4(const void* p) {
  uint4 v;
  asm volatile("{\n.reg .b128 t;\n.reg .b64 a, b;\nld.relaxed.gpu.global.b128 t, [%4];\nmov.b128 {a, b}, t;\nmov.b64 {%0, %1}, a;\nmov.b64 {%2, %3}, b;\n}\n"
               : "=r"(v.x), "=r"(v.y), "=r"(v.z), "=r"(v.w) : "l"(p) : "memory");
  return v;
}
__device__ __forceinline__ void ld_stale4(uint4& v, const void* p, uint32_t tag) {
  asm volatile("{\n.reg .b128 t;\n.reg .b64 a, b;\n.reg .b32 x;\n.reg .pred p;\n"
               "lop3.b32 x, %0, %5, 1, 0x28;\nsetp.ne.u32 p, x, 0;\n"
               "mov.b64 a, {%0, %1};\nmov.b64 b, {%2, %3};\nmov.b128 t, {a, b};\n"
               "@p ld.relaxed.gpu.global.b128 t, [%4];\n"
               "mov.b128 {a, b}, t;\nmov.b64 {%0, %1}, a;\nmov.b64 {%2, %3}, b;\n}\n"
               : "+r"(v.x), "+r"(v.y), "+r"(v.z), "+r"(v.w) : "l"(p), "r"(tag) : "memory");
}
__device__ __forceinline__ void st_tag4(void* p, float a, float b, float c, float d, uint32_t tag) {
  asm volatile("{\n.reg .b128 t;\n.reg .b64 a, b;\nmov.b64 a, {%1, %2};\nmov.b64 b, {%3, %4};\nmov.b128 t, {a, b};\nst.relaxed.gpu.global.b128 [%0], t;\n}\n"
               ::"l"(p), "r"((__float_as_uint(a) & ~1u) | tag), "f"(b), "f"(c), "f"(d) : "memory");
}
__device__ __forceinline__ uint32_t stale8(const uint4 (&f)[8], uint32_t tag) {
  uint32_t r[4];
#pragma unroll
  for (int i = 0; i < 4; i++) asm("lop3.b32 %0, %1, %2, %3, 0x7E;" : "=r"(r[i]) : "r"(f[2 * i].x), "r"(f[2 * i + 1].x), "r"(tag));
  asm("lop3.b32 %0, %0, %1, %2, 0xFE;" : "+r"(r[0]) : "r"(r[1]), "r"(r[2]));
  return r[0] | r[3];
}

struct ConvC { uint32_t a1[2][4], wa[2], wb[2], sg; };
__device__ __forceinline__ uint64_t dsc(uint32_t lo, uint32_t hi) { return ((uint64_t)hi << 32) | lo; }
__device__ __forceinline__ uint32_t hfma(uint32_t a, uint32_t b, uint32_t c) { uint32_t r; asm("fma.rn.f16x2 %0, %1, %2, %3;" : "=r"(r) : "r"(a), "r"(b), "r"(c)); return r; }
__device__ __forceinline__ uint32_t hfnma(uint32_t a, uint32_t b, uint32_t c) { uint32_t r; asm("{.reg .b32 n; neg.f16x2 n, %1; fma.rn.f16x2 %0, n, %2, %3;}" : "=r"(r) : "r"(a), "r"(b), "r"(c)); return r; }
__device__ __forceinline__ uint32_t hmul16(uint32_t a, uint32_t b) { uint32_t r; asm("mul.rn.f16x2 %0, %1, %2;" : "=r"(r) : "r"(a), "r"(b)); return r; }
template <int N> __device__ __forceinline__ void keepu(uint32_t (&d)[N]) {
#pragma unroll
  for (int i = 0; i < N; i++) asm volatile("" : "+r"(d[i])::"memory");
}
__device__ __forceinline__ void conv_m1(const ConvC& K, uint32_t (&u)[16], uint32_t l) {
  wg_fence();
  wgmma_hrs_n64<1>(u, K.a1[0][0], K.a1[0][1], K.a1[0][2], K.a1[0][3], dsc(l, 32), 0);
  wgmma_hrs_n64<1>(u, K.a1[1][0], K.a1[1][1], K.a1[1][2], K.a1[1][3], dsc(l + 16, 32), 1);
  wg_commit();
}
__device__ __forceinline__ void conv_s2(const ConvC& K, uint32_t (&u)[16], uint32_t (&Z)[2][8], uint32_t dfl) {
  uint32_t fr[8], fi[8];
#pragma unroll
  for (int c = 0; c < 8; c++) {
    const uint32_t r = hfma(K.wa[c & 1], u[2 * c + 1], u[2 * c]);
    fi[c] = hfma(K.wb[c & 1], r, u[2 * c + 1]);
    fr[c] = hfma(K.wa[c & 1], fi[c], r);
  }
  wg_fence();
#pragma unroll
  for (int p = 0; p < 2; p++) {
    wgmma_hrs_n32<0>(Z[p], fr[4 * p], fr[4 * p + 2], fr[4 * p + 1], fr[4 * p + 3], dsc(dfl, 32), 0);
    wgmma_hrs_n32<0>(Z[p], fi[4 * p], fi[4 * p + 2], fi[4 * p + 1], fi[4 * p + 3], dsc(dfl + 16, 32), 1);
  }
  wg_commit();
}
__device__ __forceinline__ void conv_win(const ConvC& K, const uint32_t (&X)[2][8], uint32_t (&W)[2][8]) {
#pragma unroll
  for (int b = 0; b < 4; b++)
#pragma unroll
    for (int c = 0; c < 2; c++) {
      const uint32_t xr = X[b >> 1][2 * c + (b & 1)], xi = X[b >> 1][4 + 2 * c + (b & 1)];
      const int a = b ? b - 1 : 0;
      W[b >> 1][2 * c + (b & 1)] = b ? hfnma(K.sg, X[a >> 1][4 + 2 * c + (a & 1)], xr) : hmul16(xr, 0x3C003C00u);
      W[b >> 1][4 + 2 * c + (b & 1)] = b ? hfma(K.sg, X[a >> 1][2 * c + (a & 1)], xi) : hmul16(xi, 0x3C003C00u);
    }
}
template <int p>
__device__ __forceinline__ void conv_pw(uint32_t (&X)[2][8], uint32_t (&H)[2][8], uint32_t (&V)[8], uint32_t dil) {
  uint32_t pr[2][2], pi[2][2];
#pragma unroll
  for (int jj = 0; jj < 2; jj++)
#pragma unroll
    for (int c = 0; c < 2; c++) {
      const int j = 2 * p + jj;
      uint32_t sr = 0, si = 0;
#pragma unroll
      for (int a = 0; a <= j; a++) {
        const int b = j - a;
        const uint32_t hr = H[a >> 1][2 * c + (a & 1)], hi = H[a >> 1][4 + 2 * c + (a & 1)];
        const uint32_t xr = X[b >> 1][2 * c + (b & 1)], xi = X[b >> 1][4 + 2 * c + (b & 1)];
        sr = a == 0 ? hmul16(hr, xr) : hfma(hr, xr, sr);
        si = a == 0 ? hmul16(hr, xi) : hfma(hr, xi, si);
        sr = hfnma(hi, xi, sr);
        si = hfma(hi, xr, si);
      }
      pr[jj][c] = sr; pi[jj][c] = si;
    }
  wg_fence();
  wgmma_hrs_n32<0>(V, pr[0][0], pr[1][0], pr[0][1], pr[1][1], dsc(dil, 32), 0);
  wgmma_hrs_n32<0>(V, pi[0][0], pi[1][0], pi[0][1], pi[1][1], dsc(dil + 16, 32), 1);
  wg_commit();
}
template <int p>
__device__ __forceinline__ void conv_it(const ConvC& K, uint32_t (&V)[8], uint32_t vst) {
#pragma unroll
  for (int jj = 0; jj < 2; jj++) {
    uint32_t wr[2], wi[2];
#pragma unroll
    for (int c = 0; c < 2; c++) {
      const uint32_t r = hfnma(K.wa[c], V[4 + 2 * c + jj], V[2 * c + jj]);
      wi[c] = hfnma(K.wb[c], r, V[4 + 2 * c + jj]);
      wr[c] = hfnma(K.wa[c], wi[c], r);
    }
    stsm4(vst + (2 * p + jj) * 2048, wr[0], wr[1], wi[0], wi[1]);
  }
}
__device__ __forceinline__ void conv_m4(uint32_t (&y)[8], uint32_t (&a)[4][4], uint32_t d4l) {
  wg_fence();
  wgmma_hrs_n32<0>(y, a[0][0], a[0][1], a[0][2], a[0][3], dsc(d4l, 64), 0);
#pragma unroll
  for (int s = 1; s < 4; s++) wgmma_hrs_n32<0>(y, a[s][0], a[s][1], a[s][2], a[s][3], dsc(d4l + s * 16, 64), 1);
  wg_commit();
}

struct Params {
  CUtensorMap tmX, tmW, tmWo, tmWo1, tmK, tmV, tmQ, tmOA, tmOB;
  const __nv_bfloat16 *shift_k, *h, *D, *x, *w, *wo, *q;
  float *part, *kv;
  uint4* o;
  unsigned *ocnt, *epoch;
  const uint32_t *thr, *img;
};

__global__ void __cluster_dims__(2, 1, 1) __launch_bounds__(384, 1) fused_kernel(const __grid_constant__ Params P) {
  extern __shared__ __align__(1024) uint8_t smem[];
  const uint32_t sb = smem_u32(smem);
  const uint32_t bars = sb + OFF_BAR;
  const int tid = threadIdx.x, lane = tid & 31;
  const int warp = __shfl_sync(~0u, tid >> 5, 0);
  const int rank = blockIdx.x & 1, cl = blockIdx.x >> 1;
  const int mb = cl >> 3, hq = cl & 7;
  const int hp = 2 * hq + rank;
  const int rb = 2 * mb + (hq >> 2), cb = hq & 3;
#define BAR(i) (bars + 8 * (i))

  if (tid == 0) { STAMP(0, 0); GSTAMP(0, 30); }
  if (warp == 8) {
    if (elect_one()) {
      mbar_init(BAR(B_FULL1), 1);
      asm volatile("fence.mbarrier_init.release.cluster;" ::: "memory");
      mbar_expect(BAR(B_FULL1), STAGE_BYTES);
      tma3d(sb + 32768, &P.tmW, hp * 64, 0, 0, BAR(B_FULL1));
    }
    if (lane == 0) STAMP(3, 21);
  } else if (lane == 0) {
    const int wi = warp - (warp > 8);
#pragma unroll
    for (int r = 0; r < 6; r++)
      if (r < 5 || wi < B_COUNT - 56) mbar_init(BAR(1 + 11 * r + wi), ((uint32_t)(bar_counts(r) >> (4 * wi)) & 15) + 1);
    asm volatile("fence.mbarrier_init.release.cluster;" ::: "memory");
  }
  if (tid == 0) STAMP(2, 6);
  asm volatile("barrier.cluster.arrive.relaxed.aligned;\nbarrier.cluster.wait.aligned;" ::: "memory");
  if (warp == 8 && elect_one()) tma2d_mc(sb + rank * 16384, &P.tmX, 0, mb * 256 + rank * 128, BAR(B_FULL1));
  if (tid == 256) STAMP(2, 7);

  if (warp < 8) {
    asm volatile("setmaxnreg.inc.sync.aligned.u32 224;");
    const int wg = warp >> 2, w = warp & 3, g = lane >> 2, q = lane & 3, t = tid & 127;
    const bool elect = (t == 0);
    const uint32_t s16 = (sb & 0x3FFFF) >> 4;
    constexpr uint32_t SW128 = 64 | (1u << 30);
    uint32_t pq[2][16], v[32];
    int ehs;
    ConvC K;
    {
      float acc[2][96];
      int st = 0, ph = 0;
#pragma unroll 1
      for (int kb = 0; kb < 14; kb++) {
        mbar_wait(BAR(B_FULL1 + st), ph);
        if (kb == 0 && elect) { STAMP(wg, 1); GSTAMP(wg, 26); }
        if (kb == 8 && elect) { STAMP(wg, 16); GSTAMP(wg, 25); }
        if (tid == 0) STAMP(2, 8 + kb);
        const uint32_t da = s16 + st * (STAGE_BYTES >> 4) + wg * 1024 + (1 << 16);
        const uint32_t db = s16 + st * (STAGE_BYTES >> 4) + 2048 + (512 << 16);
        wg_fence();
#pragma unroll
        for (int ks = 0; ks < 4; ks++) {
          wgmma_ss_n192<0, 1>(acc[0], dsc(da + ks * 2, SW128), dsc(db + ks * 128, SW128), (kb | ks) != 0);
          wgmma_ss_n192<0, 1>(acc[1], dsc(da + 512 + ks * 2, SW128), dsc(db + ks * 128, SW128), (kb | ks) != 0);
        }
        wg_commit();
        wg_wait<1>();
        if (kb > 0 && t < 2) mbar_arrive_cl(BAR(B_EMPTY1 + (st == 0 ? 2 : st - 1)), t);
        if (++st == 3) { st = 0; ph ^= 1; }
      }
#define TAIL_MMA(mt, stage) do { wg_fence(); _Pragma("unroll") for (int ks = 0; ks < 4; ks++) \
        wgmma_ss_n192<0, 1>(acc[mt], dsc(s16 + (stage) * (STAGE_BYTES >> 4) + wg * 1024 + (mt) * 512 + (1 << 16) + ks * 2, SW128), \
                            dsc(s16 + (stage) * (STAGE_BYTES >> 4) + 2048 + (512 << 16) + ks * 128, SW128), 1); wg_commit(); } while (0)
      mbar_wait(BAR(B_FULL1 + 2), 0);
      TAIL_MMA(0, 2);
      wg_wait<1>();
      if (t < 2) mbar_arrive_cl(BAR(B_EMPTY1 + 1), t);
      mbar_wait(BAR(B_FULL1 + 0), 1);
      TAIL_MMA(0, 0);
      TAIL_MMA(1, 2);
      if (!TSPLIT) TAIL_MMA(1, 0);
      const uint32_t lrow = sb + (16 * w + 8 * ((lane >> 3) & 1) + (lane & 7)) * 128 + (((lane >> 4) ^ (lane & 7)) << 4);
      const uint32_t pko = OFF_H + wg * 8192, vo0 = 6 * 16384 + wg * 8192, vo1 = 7 * 16384 + wg * 16384;
#define E1K(mt, i) do { if (opaque_true()) { _Pragma("unroll") for (int j = (i); j < (i) + 2; j++) { \
          const float* a = &acc[mt][32 + 8 * j]; const float* b = a + 32; const uint32_t o = lrow ^ (j * 32); \
          stsm4(o + ((mt) ? vo1 : vo0), pk2(b[0], b[1]), pk2(b[2], b[3]), pk2(b[4], b[5]), pk2(b[6], b[7])); \
          stsm4(o + pko + (mt) * 16384, phi2(a[0], a[1]), phi2(a[2], a[3]), phi2(a[4], a[5]), phi2(a[6], a[7])); } } } while (0)
#define E1Q(mt) do { if (opaque_true()) { _Pragma("unroll") for (int i = 0; i < 16; i++) pq[mt][i] = phi2(acc[mt][2 * i], acc[mt][2 * i + 1]); } } while (0)
      mbar_wait(BAR(B_EMPTY1 + 1), 0);
      if (TSPLIT) wg_wait<1>(); else wg_wait<2>();
      keep(acc[0]);
      if (elect) STAMP(wg, 18);
      E1K(0, 0);
      if (TSPLIT) TAIL_MMA(1, 0);
      E1K(0, 2);
      if (elect) STAMP(wg, 19);
      {
        const uint4* ct = (const uint4*)P.thr + t;
        const uint4* hp4 = (const uint4*)(P.h + (blockIdx.x * 8 + warp) * 2048) + ((lane & 15) * 2 + (lane >> 4));
#pragma unroll
        for (int i = 0; i < 8; i++) { const uint4 u = __ldg(hp4 + i * 32); v[4 * i] = u.x; v[4 * i + 1] = u.y; v[4 * i + 2] = u.z; v[4 * i + 3] = u.w; }
#pragma unroll
        for (int s = 0; s < 2; s++) { const uint4 u = __ldg(ct + s * 128); K.a1[s][0] = u.x; K.a1[s][1] = u.y; K.a1[s][2] = u.z; K.a1[s][3] = u.w; }
        const uint4 u = __ldg(ct + 2 * 128);
        K.wa[0] = u.x; K.wa[1] = u.y; K.wb[0] = u.z; K.wb[1] = u.w;
        K.sg = (lane & 4) ? 0xBC00BC00u : 0x3C003C00u;
      }
      E1Q(0);
      if (elect) STAMP(wg, 20);
      mbar_wait(BAR(B_XT), 0);
      const uint32_t tag = ~*(volatile unsigned*)(smem + OFF_EPOCH) & 1;
      wg_wait<0>();
      keep(acc[1]);
      if (t < 2) mbar_arrive_cl(BAR(B_EMPTY1 + 0), t);
      if (elect) { STAMP(wg, 2); GSTAMP(wg, 27); }
      E1K(1, 0);
      E1K(1, 2);
      fence_async();
      bar_sync(1 + wg);
      if (elect) STAMP(wg, 3);
      float kva[36];
      wg_fence();
#pragma unroll
      for (int ks = 0; ks < 8; ks++) {
        const uint32_t vb = ((ks >> 2 ? vo1 : vo0) >> 4) + (ks & 3) * 128;
        wgmma_ss_n72<1, 1>(kva, dsc(s16 + (pko >> 4) + (ks >> 2) * 1024 + (ks & 3) * 128 + (1 << 16), SW128),
                           dsc(s16 + vb + (((OFF_ONES >> 4) - vb) << 16), SW128), ks != 0);
      }
      wg_commit();
      int eh = 0;
      if (NPOS == 0) eh = normalise(v, lane == 0 ? *(const float*)(smem + OFF_D + 4 * warp) : 0.f);
      wg_wait<0>();
      keep(kva);
      if (elect) STAMP(wg, 24);
      {
        float4 p[5];
#pragma unroll
        for (int c = 0; c < 4; c++)
          p[c] = w < 2 ? make_float4(kva[4 * c], kva[4 * c + 1], kva[4 * c + 2], kva[4 * c + 3])
                       : make_float4(kva[16 + 4 * c], kva[17 + 4 * c], kva[18 + 4 * c], kva[19 + 4 * c]);
        p[4] = make_float4(kva[32], kva[34], __shfl_down_sync(~0u, kva[32], 4), __shfl_down_sync(~0u, kva[34], 4));
        float4* hand = (float4*)(smem + 8 * 16384 + 8192 - (w >> 1) * 16384) + (t & 63);
        if ((w >> 1) != wg) {
#pragma unroll
          for (int c = 0; c < 5; c++) hand[c * 64] = p[c];
          asm volatile("bar.arrive %0, 128;" ::"r"(5 + (w >> 1)) : "memory");
        } else {
          float* dst = P.part + (hp * 8 + mb) * 2176;
          asm volatile("bar.sync %0, 128;" ::"r"(5 + (w >> 1)) : "memory");
#pragma unroll
          for (int c = 0; c < 5; c++) { const float4 u = hand[c * 64]; p[c].x += u.x; p[c].y += u.y; p[c].z += u.z; p[c].w += u.w; }
#pragma unroll
          for (int c = 0; c < 5; c++)
            if (c < 4 || !(lane & 7)) st_tag4(c < 4 ? dst + (c * 128 + t) * 4 : dst + 2048 + 16 * w + 2 * g, p[c].x, p[c].y, p[c].z, p[c].w, tag);
        }
        __syncwarp();
        if (lane == 0) mbar_arrive(BAR(B_PKFREE));
      }
      if (elect) STAMP(wg, 4);
      E1Q(1);
      if (NPOS == 1) eh = normalise(v, lane == 0 ? *(const float*)(smem + OFF_D + 4 * warp) : 0.f);
      ehs = eh;
    }
    mbar_wait(BAR(B_PKFREE), 0);
    if (elect) STAMP(wg, 17);
    {
      const int e = ehs;
      uint8_t* dst = smem + OFF_H + (w & 2) * 8192 + wg * 8192 + (w & 1) * 4096 + (lane >> 4) * 512 + (lane & 15) * 16;
#pragma unroll
      for (int i = 0; i < 8; i++)
        *(uint4*)(dst + (i >> 1) * 1024 + (i & 1) * 256) = make_uint4(v[4 * i], v[4 * i + 1], v[4 * i + 2], v[4 * i + 3]);
      if (lane < 2) st_async(mapa(sb + OFF_SCALE + (8 * rank + warp) * 4, lane), min(max(e + smem[OFF_EX + warp] - 124, 1), 254) << 23, mapa(BAR(B_Y), lane));
      fence_async();
      bar_sync(1 + wg);
    }
    if (elect) STAMP(wg, 5);
    {
      const uint32_t dfl = s16 + (OFF_F2F >> 4) + (8 << 16), dil = s16 + (OFF_F2I >> 4) + (8 << 16), d4l = s16 + (OFF_F4 >> 4) + (8 << 16);
      const uint32_t xl = s16 + (OFF_XT >> 4) + 4 * wg * (XT_STRIDE >> 4) + (8 << 16);
      const uint32_t hl = s16 + (OFF_H >> 4) + wg * 512 + (8 << 16);
      uint32_t vst = sb + wg * 8192 + w * 512 + lane * 16, vld = sb + wg * 8192 + w * 2048 + lane * 16;
      uint32_t ya = mapa(sb + OFF_XT + 4 * wg * XT_STRIDE + (2 * rank + (w & 1)) * 1024 + lane * 16, w >> 1);
      const uint32_t ybar = mapa(BAR(B_Y), w >> 1);
      asm volatile("" : "+r"(vst), "+r"(vld), "+r"(ya));
      uint32_t ux[16], uh[16], X[2][8], W[2][8], H[2][8], V0[8], V1[8], y[8], a[4][4];
#define YOUT(i) do { mbar_wait(BAR(B_XFREE + 4 * wg + (i)), 0); \
        st_async4(ya + (i) * XT_STRIDE, y[0], y[2], y[4], y[6], ybar); \
        st_async4(ya + (i) * XT_STRIDE + 512, y[1], y[3], y[5], y[7], ybar); } while (0)
      conv_m1(K, ux, xl);
      conv_m1(K, uh, hl);
      wg_wait<1>(); keepu(ux);
      if (lane == 0) mbar_arrive_cl(BAR(B_XFREE + 4 * wg), rank ^ 1);
      conv_s2(K, ux, X, dfl);
      wg_wait<1>(); keepu(uh);
      conv_s2(K, uh, H, dfl);
      wg_wait<1>(); keepu(X[0]); keepu(X[1]);
      conv_win(K, X, W);
      wg_wait<0>(); keepu(H[0]); keepu(H[1]);
#pragma unroll 1
      for (int i = 0; i < 3; i++) {
        if (i == (wg ? OC1 : OC0)) {
          if (elect) STAMP(wg, 8);
          mbar_wait(BAR(B_KV), 0);
          if (elect) STAMP(wg, 9);
          float oa[4][20];
          wg_fence();
#pragma unroll
          for (int m = 0; m < 8; m++) {
            const uint32_t* p = &pq[m >> 2][4 * (m & 3)];
            wgmma_rs_n40<1>(oa[m >> 1], p[0], p[1], p[2], p[3], dsc(s16 + (OFF_KVB >> 4) + ((m >> 1) & 1) * 160 + (m & 1) * 16 + (8 << 16), 32), m & 1);
          }
          wg_commit();
          uint4* ot = P.o + ((2 * mb + wg) * 16 + hp) * 1024 + (16 * w + g) * 8;
          wg_wait<0>();
#pragma unroll
          for (int m = 0; m < 4; m++) {
            float (&o)[20] = oa[m];
            keep(o);
            const uint32_t den = hadd(pk2(o[16], o[18]), 0x35863586u);
#pragma unroll
            for (int r = 0; r < 2; r++) {
              const float ri = rcp_fast(__uint_as_float(r ? (den & 0xFFFF0000u) : (den << 16)));
              uint4 u;
              u.x = pk2(o[2 * r] * ri, o[2 * r + 1] * ri);
              u.y = pk2(o[4 + 2 * r] * ri, o[5 + 2 * r] * ri);
              u.z = pk2(o[8 + 2 * r] * ri, o[9 + 2 * r] * ri);
              u.w = pk2(o[12 + 2 * r] * ri, o[13 + 2 * r] * ri);
              __stcg(ot + (64 * (m >> 1) + 8 * r) * 8 + ((4 * (m & 1) + q) ^ g), u);
            }
          }
          __syncwarp();
          if (lane == 0) mbar_arrive(BAR(B_ODONE));
          if (elect) STAMP(wg, 10);
        }
        const int n = i + 1;
        const uint32_t vo = (i & 1) ? OFF_H : OFF_VP;
        conv_m1(K, ux, xl + n * (XT_STRIDE >> 4));
        conv_m1(K, uh, hl + (n >> 1) * 1024 + (n & 1) * 256);
        conv_pw<0>(W, H, V0, dil);
        conv_pw<1>(W, H, V1, dil);
        wg_wait<2>(); keepu(ux); keepu(uh);
        if (lane == 0) mbar_arrive_cl(BAR(B_XFREE + 4 * wg + n), rank ^ 1);
        conv_s2(K, ux, X, dfl);
        wg_wait<1>(); keepu(V0); keepu(V1);
        conv_it<0>(K, V0, vst + vo);
        conv_it<1>(K, V1, vst + vo);
        bar_sync(1 + wg);
#pragma unroll
        for (int s = 0; s < 4; s++) ldsm4t(a[s], vld + vo + s * 512);
        conv_s2(K, uh, H, dfl);
        conv_m4(y, a, d4l);
        if (i > 0 && lane < 2) mbar_arrive_cl(BAR(B_AFREE + i - 1), lane);
        wg_wait<2>(); keepu(X[0]); keepu(X[1]);
        conv_win(K, X, W);
        wg_wait<0>(); keepu(H[0]); keepu(H[1]); keepu(y);
        YOUT(i);
        if (elect) STAMP(wg, i < 2 ? 6 + i : 9 + i);
      }
      conv_pw<0>(W, H, V0, dil);
      conv_pw<1>(W, H, V1, dil);
      wg_wait<1>(); keepu(V0);
      conv_it<0>(K, V0, vst + OFF_H + 16384);
      wg_wait<0>(); keepu(V1);
      conv_it<1>(K, V1, vst + OFF_H + 16384);
      bar_sync(1 + wg);
#pragma unroll
      for (int s = 0; s < 4; s++) ldsm4t(a[s], vld + OFF_H + 16384 + s * 512);
      conv_m4(y, a, d4l);
      if (lane < 2) mbar_arrive_cl(BAR(B_AFREE + 2), lane);
      wg_wait<0>(); keepu(y);
      YOUT(3);
      if (lane == 0) mbar_arrive(BAR(B_Y));
      if (elect) STAMP(wg, 12);
    }
    {
      float acc[64];
#pragma unroll 1
      for (int kb = 0; kb < 16; kb++) {
        mbar_wait(BAR(B_FULL2 + kb), 0);
        if (kb == 0 && elect) { STAMP(wg, 13); GSTAMP(wg, 28); }
        const uint32_t da = s16 + ((uint32_t)(SLOT_A >> (4 * kb)) & 15) * 1024 + wg * 512 + (1 << 16);
        const uint32_t db = s16 + ((uint32_t)(SLOT_B >> (4 * kb)) & 15) * 1024 + (512 << 16);
        wg_fence();
#pragma unroll
        for (int ks = 0; ks < 4; ks++) wgmma_ss_n128<0, 1>(acc, dsc(da + ks * 2, SW128), dsc(db + ks * 128, SW128), (kb | ks) != 0);
        wg_commit();
        wg_wait<1>();
        if (kb > 0 && kb < 14 && t < 2 && (kb <= 11 || t == rank)) mbar_arrive_cl(BAR(B_CONS2 + kb - 1), t);
      }
      wg_wait<0>();
      keep(acc);
      if (elect) { STAMP(wg, 14); GSTAMP(wg, 29); }
      mbar_wait(BAR(B_CONS2 + 12), 0);
      const uint32_t stg = sb + (wg ? 5 : 0) * 16384;
      const uint32_t lrow = stg + (16 * w + 8 * ((lane >> 3) & 1) + (lane & 7)) * 128 + (((lane >> 4) ^ (lane & 7)) << 4);
#pragma unroll
      for (int cp = 0; cp < 8; cp++) {
        const float* a = &acc[8 * cp];
        stsm4((lrow ^ ((cp & 3) * 32)) + (cp >> 2) * 8192, pk2(a[0], a[1]), pk2(a[2], a[3]), pk2(a[4], a[5]), pk2(a[6], a[7]));
      }
      fence_async();
      bar_sync(1 + wg);
      if (elect) {
        const int col = 1024 + 256 * cb + 128 * rank, row = 128 * rb + 64 * wg;
        tma2d_st(&P.tmOB, stg, col, row);
        tma2d_st(&P.tmOB, stg + 8192, col + 64, row);
        asm volatile("cp.async.bulk.commit_group;\ncp.async.bulk.wait_group.read 0;" ::: "memory");
        STAMP(wg, 15); GSTAMP(wg, 31); PDUMP(wg);
      }
    }
  } else {
    asm volatile("setmaxnreg.dec.sync.aligned.u32 56;");
    if (warp == 8) {
      if (lane == 0) STAMP(3, 20);
      int st = 1, ph = 1;
      const uint8_t* pfx = (const uint8_t*)P.x + (mb * 256 + hp * 16 + (lane & 15)) * 2048;
      const uint8_t* pfw = (const uint8_t*)P.w + (mb * 8 + (lane & 7)) * 6144 + (lane >> 3) * 2048 + hp * 128;
#pragma unroll 1
      for (int kb = 1; kb < 16; kb++) {
        if (kb >= 3) mbar_wait(BAR(B_EMPTY1 + st), ph);
        const uint32_t sa = sb + st * STAGE_BYTES;
        if (elect_one()) {
          mbar_expect(BAR(B_FULL1 + st), STAGE_BYTES);
          tma2d_mc(sa + rank * 16384, &P.tmX, kb * 64, mb * 256 + rank * 128, BAR(B_FULL1 + st));
          tma3d(sa + 32768, &P.tmW, hp * 64, kb * 64, 0, BAR(B_FULL1 + st));
        }
        if (kb == 1 && lane == 0) STAMP(2, 24);
        if (PFD && kb >= 2) {
#pragma unroll 1
          for (int j = kb == 2 ? 3 : kb + PFD; j <= kb + PFD && j < 16; j++) {
            if (lane < 16) asm volatile("prefetch.global.L2 [%0];" ::"l"(pfx + j * 128));
            if (lane < 24) asm volatile("prefetch.global.L2 [%0];" ::"l"(pfw + j * (64 * 6144)));
          }
          if (kb >= QPF && kb < QPF + 8) asm volatile("prefetch.global.L2 [%0];" ::"l"((const uint8_t*)P.q + (blockIdx.x * 256 + (kb - QPF) * 32 + lane) * 128));
          if (kb >= 4)
            asm volatile("prefetch.global.L2 [%0];" ::"l"(kb < 12 ? (const uint8_t*)P.h + (blockIdx.x * 256 + (kb - 4) * 32 + lane) * 128
                                                                  : (const uint8_t*)P.wo + (blockIdx.x * 128 + (kb - 12) * 32 + lane) * 128));
        }
        if (++st == 3) { st = 0; ph ^= 1; }
      }
      if (lane == 0) STAMP(2, 1);
      const unsigned epoch = P.epoch[blockIdx.x];
#define SLOT(tab, kb) (sb + ((uint32_t)((tab) >> (4 * (kb))) & 15) * 16384)
#define LOAD_B(kb) tma3d(SLOT(SLOT_B, kb), &P.tmWo, 0, (kb) * 64, 4 * cb + 2 * rank, BAR(B_FULL2 + (kb)))
#define LOAD_A(kb) bulk_ld_mc(SLOT(SLOT_A, kb) + rank * 8192, P.o + (rb * 16 + (kb)) * 1024 + rank * 512, 8192, BAR(B_FULL2 + (kb)))
      mbar_wait(BAR(B_EMPTY1 + 0), 1);
      {
        const uint32_t c0 = clock();
#pragma unroll 1
        for (int i = 0; i < 14; i++) {
          const int kb = i >> 1;
          if (i == 8) mbar_wait(BAR(B_PKFREE), 0);
          while ((uint32_t)clock() - c0 < i * BPACE) __nanosleep(32);
          if (elect_one()) {
            if (!(i & 1)) mbar_expect(BAR(B_FULL2 + kb), 16384);
            tma3d(SLOT(SLOT_B, kb) + (i & 1) * 8192, &P.tmWo1, 0, kb * 64, 4 * cb + 2 * rank + (i & 1), BAR(B_FULL2 + kb));
            if (i == 0) mbar_expect(BAR(B_Q), 8192);
            if (i < 4) tma3d(sb + OFF_SPARE + 2048 * i, &P.tmQ, 16 * cl, 64 * rank + 32 * (i >> 1), 2 * ((i + 6) & 7), BAR(B_Q));
          }
        }
      }
      if (lane == 0) STAMP(2, 2);
      poll_ge(&P.ocnt[rb * 32], 16 * (epoch + 1));
      asm volatile("fence.proxy.async.global;" ::: "memory");
      if (lane == 0) STAMP(2, 3);
#pragma unroll 1
      for (int kb = 0; kb < 7; kb++) {
        mbar_wait(BAR(kb < 3 ? B_AFREE + kb : B_CONS2 + ((kb - 3) >> 1)), 0);
        if (elect_one()) {
          mbar_expect(BAR(B_FULL2 + kb), 16384);
          LOAD_A(kb);
        }
        if (kb == 2 && lane == 0) STAMP(2, 4);
        if (kb == 0 && lane == 0) STAMP(3, 23);
      }
#pragma unroll 1
      for (int kb = 7; kb < 16; kb++) {
        mbar_wait(BAR(B_CONS2 + kb - 5), 0);
        if (elect_one()) { mbar_expect(BAR(B_FULL2 + kb), 32768); LOAD_A(kb); LOAD_B(kb); }
      }
      if (lane == 0) { P.epoch[blockIdx.x] = epoch + 1; STAMP(2, 5); PDUMP(2); }
    } else {
      const uint32_t clk0 = clock();
      const int hw = warp - 9, g = lane >> 2, q = lane & 3;
      const unsigned epoch = P.epoch[blockIdx.x];
      const uint32_t tag = ~epoch & 1;
      const uint32_t stg = sb + OFF_STG + hw * STG_STRIDE, sbar = BAR(B_STG + 2 * hw);
      int ph = 0;
      {
        uint32_t tap[2][4];
#pragma unroll
        for (int cg = 0; cg < 2; cg++) {
          const uint2 u = __ldg((const uint2*)(P.shift_k + (16 * cl + 8 * cg + g) * 4));
          tap[cg][0] = __byte_perm(u.x, 0, 0x1010); tap[cg][1] = __byte_perm(u.x, 0, 0x3232);
          tap[cg][2] = __byte_perm(u.y, 0, 0x1010); tap[cg][3] = __byte_perm(u.y, 0, 0x3232);
        }
        if (hw == 0 && lane < 8) *(float*)(smem + OFF_D + 4 * lane) = __bfloat162float(P.D[blockIdx.x * 8 + lane]);
        if (hw == 1) asm volatile("prefetch.global.L2 [%0];" ::"l"(P.thr + (lane + 32 * (blockIdx.x & 1)) * 32));
        if (hw == 0 && elect_one()) {
          *(volatile unsigned*)(smem + OFF_EPOCH) = epoch;
          mbar_expect(BAR(B_XRAW), 32768);
          mbar_expect(BAR(B_Y), 32768 + 64);
        }
        for (int i = hw * 32 + lane; i < 528; i += 96) st_tag4(P.part + (hp * 8 + mb) * 2176 + 4 * i, 0.f, 0.f, 0.f, 0.f, tag ^ 1);
        if (hw < 2 || lane < 2) st_tag4(P.kv + hp * 2176 + (4 * (hw < 2 ? 64 * mb + 32 * hw + lane : 512 + 2 * mb + lane)), 0.f, 0.f, 0.f, 0.f, tag ^ 1);
        if (lane == 0) STAMP(3, hw);
        const uint32_t xo = sb + OFF_XT + g * XT_STRIDE + rank * 2048 + q * 4;
        const int krow = 8 + (lane & 7) - (lane >> 3);
        const uint32_t ka = stg + krow * 32 + ((krow & 4) << 2), va = stg + 2304 + lane * 32 + ((lane & 4) << 2);
        int b = 0;
#pragma unroll 1
        for (int ci = hw - 3; ci < 16; ci += 3) {
          const uint32_t bo = b ? OFF_F2F - OFF_STG : 0, bn = b ? 0 : OFF_F2F - OFF_STG;
          if (ci + 3 < 16) {
            while ((uint32_t)clock() - clk0 < HSTART + (ci + 3) * PACE) __nanosleep(64);
            if (elect_one()) {
              mbar_expect(sbar + 8 * (b ^ 1), 2304 + 2048);
              tma2d(stg + bn, &P.tmK, 16 * cl, 1024 * rank + 64 * (ci + 3) - 8, sbar + 8 * (b ^ 1));
              tma2d(stg + bn + 2304, &P.tmV, 16 * cl, 1024 * rank + 64 * (ci + 3), sbar + 8 * (b ^ 1));
            }
          }
          if (ci >= 0) {
            mbar_wait(sbar + 8 * b, (ph >> b) & 1);
            ph ^= 1 << b;
#pragma unroll 1
            for (int grp = 0; grp < 2; grp++) {
#pragma unroll
              for (int cg = 0; cg < 2; cg++) {
                const uint32_t dst = mapa(xo + (ci >> 3) * 1024 + ((ci & 7) * 4 + 2 * grp) * 16, cg), xbar = mapa(BAR(B_XRAW), cg);
                uint32_t vv[4], kk[4][4];
                ldsm4t(vv, (va ^ (cg * 16)) + bo + grp * 1024);
#pragma unroll
                for (int rg = 0; rg < 4; rg++) ldsm4t(kk[rg], (ka ^ (cg * 16)) + bo + grp * 1024 + rg * 256);
#pragma unroll
                for (int rg = 0; rg < 4; rg++)
                  vv[rg] = hmul(hadd(hadd(hadd(hmul(kk[rg][3], tap[cg][3]), hmul(kk[rg][2], tap[cg][2])), hmul(kk[rg][1], tap[cg][1])), hmul(kk[rg][0], tap[cg][0])), vv[rg]);
#pragma unroll
                for (int rg = 0; rg < 4; rg++) st_async(dst + (rg & 1) * 512 + (rg >> 1) * 16, vv[rg], xbar);
              }
            }
          }
          b ^= 1;
        }
      }
      if (lane == 0) STAMP(3, 3 + hw);
      asm volatile("bar.sync 4, 96;" ::: "memory");
      if (hw == 0 && elect_one()) { mbar_expect(BAR(B_XT), 10240); bulk_ld(sb + OFF_F2F, P.img, 10240, BAR(B_XT)); }
      mbar_wait(BAR(B_XRAW), 0);
#pragma unroll 1
      for (int c = hw; c < 8; c += 3) {
        uint4* p = (uint4*)(smem + OFF_XT + c * XT_STRIDE) + lane;
        uint32_t v[32];
#pragma unroll
        for (int i = 0; i < 8; i++) { const uint4 u = p[i * 32]; v[4 * i] = u.x; v[4 * i + 1] = u.y; v[4 * i + 2] = u.z; v[4 * i + 3] = u.w; }
        const int e = normalise(v, 0.f);
#pragma unroll
        for (int i = 0; i < 8; i++) p[i * 32] = make_uint4(v[4 * i], v[4 * i + 1], v[4 * i + 2], v[4 * i + 3]);
        if (lane == 0) smem[OFF_EX + c] = e;
        if (c < 6 && elect_one()) {
          if (c < 3) mbar_expect(sbar, 4096);
          tma3d(sb + OFF_STG + 2048 * c, &P.tmQ, 16 * cl, 64 * rank, 2 * c, sbar);
        }
      }
      fence_async();
      __syncwarp();
      if (lane == 0) { mbar_arrive(BAR(B_XT)); STAMP(3, 13 + hw); }
      mbar_wait(BAR(B_PKFREE), 0);
      if (hw == 0 && lane == 0) STAMP(3, 19);
      if (PD1) __nanosleep(PD1);
      {
        const int pi = hw < 2 ? 64 * mb + 32 * hw + lane : 512 + 2 * mb + (lane & 1);
        const float* psrc = P.part + hp * 8 * 2176 + 4 * pi;
        uint4 f[8];
#pragma unroll
        for (int p = 0; p < 8; p++) f[p] = ld_rlx4(psrc + p * 2176);
        if (!opaque_true()) __trap();
#pragma unroll 1
        for (int n = 0; __any_sync(~0u, stale8(f, tag) & 1); n++) {
#pragma unroll
          for (int p = 0; p < 8; p++) ld_stale4(f[p], psrc + p * 2176, tag);
          if (n > SPIN_LIMIT) __trap();
        }
        float s0 = 0.f, s1 = 0.f, s2 = 0.f, s3 = 0.f;
#pragma unroll
        for (int p = 0; p < 8; p++) { s0 += __uint_as_float(f[p].x); s1 += __uint_as_float(f[p].y); s2 += __uint_as_float(f[p].z); s3 += __uint_as_float(f[p].w); }
        if (hw < 2 || lane < 2) st_tag4(P.kv + hp * 2176 + (4 * pi), s0, s1, s2, s3, tag);
      }
      if (lane == 0 && hw == 0) STAMP(3, 8);
      if (hw == 2) {
        mbar_wait(BAR(B_ODONE), 0);
        if (lane < 2) {
          asm volatile("red.release.gpu.global.add.u32 [%0], 1;" ::"l"(&P.ocnt[(2 * mb + lane) * 32]) : "memory");
        }
        if (lane == 0) STAMP(3, 7);
        __syncwarp();
      } else {
        if (PD2) __nanosleep(PD2);
        const int t = hw * 32 + lane;
        uint4 f[8];
        const float* src = P.kv + hp * 2176 + (4 * t);
        const float* zsrc = P.kv + hp * 2176 + (2048 + (t & 48) + 2 * (lane & 6));
        uint4 zp = ld_rlx4(zsrc);
#pragma unroll
        for (int p = 0; p < 8; p++) f[p] = ld_rlx4(src + 4 * ((p & 3) * 128 + (p >> 2) * 64));
        if (!opaque_true()) __trap();
#pragma unroll 1
        for (int n = 0; __any_sync(~0u, (stale8(f, tag) | (zp.x ^ tag)) & 1); n++) {
          ld_stale4(zp, zsrc, tag);
#pragma unroll
          for (int p = 0; p < 8; p++) ld_stale4(f[p], src + 4 * ((p & 3) * 128 + (p >> 2) * 64), tag);
          if (n > SPIN_LIMIT) __trap();
        }
#define PK2U(a, b) pk2(__uint_as_float(a), __uint_as_float(b))
#pragma unroll
        for (int hh = 0; hh < 2; hh++) {
          const uint4* ff = &f[4 * hh];
          uint8_t* dst = smem + OFF_KVB + hh * 2560 + q * 512 + (16 * hw + g) * 16;
          *(uint4*)dst = make_uint4(PK2U(ff[0].x, ff[0].y), PK2U(ff[1].x, ff[1].y), PK2U(ff[2].x, ff[2].y), PK2U(ff[3].x, ff[3].y));
          *(uint4*)(dst + 128) = make_uint4(PK2U(ff[0].z, ff[0].w), PK2U(ff[1].z, ff[1].w), PK2U(ff[2].z, ff[2].w), PK2U(ff[3].z, ff[3].w));
        }
        const uint32_t zf = (lane & 1) ? ((lane & 8) ? zp.w : zp.z) : ((lane & 8) ? zp.y : zp.x);
        const uint32_t zz = PK2U(zf, zf);
        *(uint4*)(smem + OFF_KVB + hw * 2560 + 2048 + lane * 16) = make_uint4(zz, zz, zz, zz);
        fence_async();
        __syncwarp();
        if (lane == 0) { mbar_arrive(BAR(B_KV)); if (hw == 0) STAMP(3, 9); }
      }
#define QBUF(ci) (sb + 2048 * (ci) + ((ci) < 6 ? OFF_STG : (ci) < 10 ? OFF_SPARE - 6 * 2048 : OFF_F2F - 10 * 2048))
      mbar_wait(BAR(B_Y), 0);
      if (elect_one()) {
        mbar_expect(sbar + 8, 4096);
#pragma unroll 1
        for (int ci = hw ? hw + 9 : 12; ci < 16; ci += 3) tma3d(QBUF(ci), &P.tmQ, 16 * cl, 64 * rank + 32, 2 * (ci & 7), sbar + 8);
      }
      mbar_wait(BAR(B_Q), 0);
      {
        const float2 sc0 = *(const float2*)(smem + OFF_SCALE + 8 * q), sc1 = *(const float2*)(smem + OFF_SCALE + 32 + 8 * q);
        const uint32_t yl = sb + OFF_XT + (lane & 7) * XT_STRIDE + (lane >> 3) * 16;
#pragma unroll 1
        for (int ci = hw; ci < 16; ci += 3) {
          const uint32_t qb = QBUF(ci);
          const int b = ci >= 10;
          mbar_wait(sbar + 8 * b, (ph >> b) & 1);
#pragma unroll 1
          for (int nl = 0; nl < 2; nl++) {
            uint32_t yy[2][4], qq[2][4];
            const uint32_t qa = qb + lane * 32 + ((lane & 4) << 2) + nl * 1024;
#pragma unroll
            for (int cg = 0; cg < 2; cg++) { ldsm4t(yy[cg], yl + cg * 2048 + (2 * ci + nl) * 64); ldsm4(qq[cg], qa ^ (cg * 16)); }
#pragma unroll
            for (int cg = 0; cg < 2; cg++) {
              const float2 sc = cg ? sc1 : sc0;
#pragma unroll
              for (int m = 0; m < 4; m++) {
                const float2 f = __half22float2(*(const __half2*)&yy[cg][m]);
                qq[cg][m] = hmul(qq[cg][m], pk2(f.x * sc.x, f.y * sc.y));
              }
              stsm4(qa ^ (cg * 16), qq[cg][0], qq[cg][1], qq[cg][2], qq[cg][3]);
            }
          }
          fence_async();
          __syncwarp();
          if (elect_one()) tma3d_st(&P.tmOA, qb, 16 * cl, 64 * rank + 32 * (ci >> 3), 2 * (ci & 7));
        }
        asm volatile("cp.async.bulk.commit_group;\ncp.async.bulk.wait_group.read 0;" ::: "memory");
      }
      if (lane == 0) STAMP(3, 10 + hw);
    }
  }
}

typedef CUresult (*EncodeFn)(CUtensorMap*, CUtensorMapDataType, cuuint32_t, void*, const cuuint64_t*, const cuuint64_t*,
                             const cuuint32_t*, const cuuint32_t*, CUtensorMapInterleave, CUtensorMapSwizzle,
                             CUtensorMapL2promotion, CUtensorMapFloatOOBfill);

static void enc(EncodeFn fn, CUtensorMap* m, const void* p, int rank, const cuuint64_t* dims, const cuuint64_t* strides,
                const cuuint32_t* box, CUtensorMapSwizzle swz, CUtensorMapL2promotion promo) {
  cuuint32_t es[3] = {1, 1, 1};
  fn(m, CU_TENSOR_MAP_DATA_TYPE_BFLOAT16, rank, (void*)p, dims, strides, box, es, CU_TENSOR_MAP_INTERLEAVE_NONE, swz, promo,
     CU_TENSOR_MAP_FLOAT_OOB_FILL_NONE);
}

extern "C" void kernel_launch(void* const* d_in, const int* in_sizes, int n_in, void* d_out, int out_size) {
  void* fp = nullptr;
  cudaDriverEntryPointQueryResult qr;
  cudaGetDriverEntryPoint("cuTensorMapEncodeTiled", &fp, cudaEnableDefault, &qr);
  EncodeFn fn = (EncodeFn)fp;
  Params P;
  P.shift_k = (const __nv_bfloat16*)d_in[3]; P.h = (const __nv_bfloat16*)d_in[4]; P.D = (const __nv_bfloat16*)d_in[5];
  P.q = (const __nv_bfloat16*)d_in[0];
  cudaGetSymbolAddress((void**)&P.part, g_part); cudaGetSymbolAddress((void**)&P.kv, g_kv); cudaGetSymbolAddress((void**)&P.o, g_o);
  cudaGetSymbolAddress((void**)&P.ocnt, g_ocnt); cudaGetSymbolAddress((void**)&P.epoch, g_epoch);
  cudaGetSymbolAddress((void**)&P.thr, c_thr); cudaGetSymbolAddress((void**)&P.img, c_img);
  P.x = (const __nv_bfloat16*)d_in[6]; P.w = (const __nv_bfloat16*)d_in[7]; P.wo = (const __nv_bfloat16*)d_in[8];
  const CUtensorMapSwizzle S128 = CU_TENSOR_MAP_SWIZZLE_128B, S32 = CU_TENSOR_MAP_SWIZZLE_32B;
  const CUtensorMapL2promotion P0 = CU_TENSOR_MAP_L2_PROMOTION_NONE, P128 = CU_TENSOR_MAP_L2_PROMOTION_L2_128B;
  { cuuint64_t d[2] = {1024, 2048}, s[1] = {2048}; cuuint32_t b[2] = {64, 128}; enc(fn, &P.tmX, d_in[6], 2, d, s, b, S128, P128); }
  { cuuint64_t d[3] = {1024, 1024, 3}, s[2] = {6144, 2048}; cuuint32_t b[3] = {64, 64, 3}; enc(fn, &P.tmW, d_in[7], 3, d, s, b, S128, P128); }
  { cuuint64_t d[3] = {64, 1024, 16}, s[2] = {2048, 128}; cuuint32_t b[3] = {64, 64, 2}; enc(fn, &P.tmWo, d_in[8], 3, d, s, b, S128, P128); }
  { cuuint64_t d[3] = {64, 1024, 16}, s[2] = {2048, 128}; cuuint32_t b[3] = {64, 64, 1}; enc(fn, &P.tmWo1, d_in[8], 3, d, s, b, S128, P128); }
  { cuuint64_t d[2] = {1024, 2048}, s[1] = {2048}; cuuint32_t b[2] = {16, 72}; enc(fn, &P.tmK, d_in[1], 2, d, s, b, S32, PKV); }
  { cuuint64_t d[2] = {1024, 2048}, s[1] = {2048}; cuuint32_t b[2] = {16, 64}; enc(fn, &P.tmV, d_in[2], 2, d, s, b, S32, PKV); }
  { cuuint64_t d[3] = {1024, 128, 16}, s[2] = {32768, 2048}; cuuint32_t b[3] = {16, 32, 2}; enc(fn, &P.tmQ, d_in[0], 3, d, s, b, S32, PKV); }
  { cuuint64_t d[3] = {1024, 128, 16}, s[2] = {65536, 4096}; cuuint32_t b[3] = {16, 32, 2}; enc(fn, &P.tmOA, d_out, 3, d, s, b, S32, P0); }
  { cuuint64_t d[2] = {2048, 2048}, s[1] = {4096}; cuuint32_t b[2] = {64, 64}; enc(fn, &P.tmOB, d_out, 2, d, s, b, S128, P0); }
  cudaFuncSetAttribute(fused_kernel, cudaFuncAttributeMaxDynamicSharedMemorySize, SMEM_TOTAL);
  fused_kernel<<<128, 384, SMEM_TOTAL>>>(P);
}
```

```cpp
#include <cuda_runtime.h>
#include <cuda_bf16.h>
#include <cuda_fp16.h>
#include <cuda.h>
#include <stdint.h>

template<int TA, int TB, int SA=1> __device__ __forceinline__ void wgmma_ss_n192(float (&d)[96], uint64_t da, uint64_t db, int scale_d) {
  asm volatile("{\n.reg .pred p;\nsetp.ne.b32 p, %98, 0;\n"
    "wgmma.mma_async.sync.aligned.m64n192k16.f32.bf16.bf16 {%0, %1, %2, %3, %4, %5, %6, %7, %8, %9, %10, %11, %12, %13, %14, %15, %16, %17, %18, %19, %20, %21, %22, %23, %24, %25, %26, %27, %28, %29, %30, %31, %32, %33, %34, %35, %36, %37, %38, %39, %40, %41, %42, %43, %44, %45, %46, %47, %48, %49, %50, %51, %52, %53, %54, %55, %56, %57, %58, %59, %60, %61, %62, %63, %64, %65, %66, %67, %68, %69, %70, %71, %72, %73, %74, %75, %76, %77, %78, %79, %80, %81, %82, %83, %84, %85, %86, %87, %88, %89, %90, %91, %92, %93, %94, %95}, %96, %97, p, %101, 1, %99, %100;\n}\n"
    : "+f"(d[0]), "+f"(d[1]), "+f"(d[2]), "+f"(d[3]), "+f"(d[4]), "+f"(d[5]), "+f"(d[6]), "+f"(d[7]), "+f"(d[8]), "+f"(d[9]), "+f"(d[10]), "+f"(d[11]), "+f"(d[12]), "+f"(d[13]), "+f"(d[14]), "+f"(d[15]), "+f"(d[16]), "+f"(d[17]), "+f"(d[18]), "+f"(d[19]), "+f"(d[20]), "+f"(d[21]), "+f"(d[22]), "+f"(d[23]), "+f"(d[24]), "+f"(d[25]), "+f"(d[26]), "+f"(d[27]), "+f"(d[28]), "+f"(d[29]), "+f"(d[30]), "+f"(d[31]), "+f"(d[32]), "+f"(d[33]), "+f"(d[34]), "+f"(d[35]), "+f"(d[36]), "+f"(d[37]), "+f"(d[38]), "+f"(d[39]), "+f"(d[40]), "+f"(d[41]), "+f"(d[42]), "+f"(d[43]), "+f"(d[44]), "+f"(d[45]), "+f"(d[46]), "+f"(d[47]), "+f"(d[48]), "+f"(d[49]), "+f"(d[50]), "+f"(d[51]), "+f"(d[52]), "+f"(d[53]), "+f"(d[54]), "+f"(d[55]), "+f"(d[56]), "+f"(d[57]), "+f"(d[58]), "+f"(d[59]), "+f"(d[60]), "+f"(d[61]), "+f"(d[62]), "+f"(d[63]), "+f"(d[64]), "+f"(d[65]), "+f"(d[66]), "+f"(d[67]), "+f"(d[68]), "+f"(d[69]), "+f"(d[70]), "+f"(d[71]), "+f"(d[72]), "+f"(d[73]), "+f"(d[74]), "+f"(d[75]), "+f"(d[76]), "+f"(d[77]), "+f"(d[78]), "+f"(d[79]), "+f"(d[80]), "+f"(d[81]), "+f"(d[82]), "+f"(d[83]), "+f"(d[84]), "+f"(d[85]), "+f"(d[86]), "+f"(d[87]), "+f"(d[88]), "+f"(d[89]), "+f"(d[90]), "+f"(d[91]), "+f"(d[92]), "+f"(d[93]), "+f"(d[94]), "+f"(d[95])
    : "l"(da), "l"(db), "r"(scale_d), "n"(TA), "n"(TB), "n"(SA));
}
template<int TA, int TB, int SA=1> __device__ __forceinline__ void wgmma_ss_n128(float (&d)[64], uint64_t da, uint64_t db, int scale_d) {
  asm volatile("{\n.reg .pred p;\nsetp.ne.b32 p, %66, 0;\n"
    "wgmma.mma_async.sync.aligned.m64n128k16.f32.bf16.bf16 {%0, %1, %2, %3, %4, %5, %6, %7, %8, %9, %10, %11, %12, %13, %14, %15, %16, %17, %18, %19, %20, %21, %22, %23, %24, %25, %26, %27, %28, %29, %30, %31, %32, %33, %34, %35, %36, %37, %38, %39, %40, %41, %42, %43, %44, %45, %46, %47, %48, %49, %50, %51, %52, %53, %54, %55, %56, %57, %58, %59, %60, %61, %62, %63}, %64, %65, p, %69, 1, %67, %68;\n}\n"
    : "+f"(d[0]), "+f"(d[1]), "+f"(d[2]), "+f"(d[3]), "+f"(d[4]), "+f"(d[5]), "+f"(d[6]), "+f"(d[7]), "+f"(d[8]), "+f"(d[9]), "+f"(d[10]), "+f"(d[11]), "+f"(d[12]), "+f"(d[13]), "+f"(d[14]), "+f"(d[15]), "+f"(d[16]), "+f"(d[17]), "+f"(d[18]), "+f"(d[19]), "+f"(d[20]), "+f"(d[21]), "+f"(d[22]), "+f"(d[23]), "+f"(d[24]), "+f"(d[25]), "+f"(d[26]), "+f"(d[27]), "+f"(d[28]), "+f"(d[29]), "+f"(d[30]), "+f"(d[31]), "+f"(d[32]), "+f"(d[33]), "+f"(d[34]), "+f"(d[35]), "+f"(d[36]), "+f"(d[37]), "+f"(d[38]), "+f"(d[39]), "+f"(d[40]), "+f"(d[41]), "+f"(d[42]), "+f"(d[43]), "+f"(d[44]), "+f"(d[45]), "+f"(d[46]), "+f"(d[47]), "+f"(d[48]), "+f"(d[49]), "+f"(d[50]), "+f"(d[51]), "+f"(d[52]), "+f"(d[53]), "+f"(d[54]), "+f"(d[55]), "+f"(d[56]), "+f"(d[57]), "+f"(d[58]), "+f"(d[59]), "+f"(d[60]), "+f"(d[61]), "+f"(d[62]), "+f"(d[63])
    : "l"(da), "l"(db), "r"(scale_d), "n"(TA), "n"(TB), "n"(SA));
}
template<int TA, int TB, int SA=1> __device__ __forceinline__ void wgmma_ss_n72(float (&d)[36], uint64_t da, uint64_t db, int scale_d) {
  asm volatile("{\n.reg .pred p;\nsetp.ne.b32 p, %38, 0;\n"
    "wgmma.mma_async.sync.aligned.m64n72k16.f32.bf16.bf16 {%0, %1, %2, %3, %4, %5, %6, %7, %8, %9, %10, %11, %12, %13, %14, %15, %16, %17, %18, %19, %20, %21, %22, %23, %24, %25, %26, %27, %28, %29, %30, %31, %32, %33, %34, %35}, %36, %37, p, %41, 1, %39, %40;\n}\n"
    : "+f"(d[0]), "+f"(d[1]), "+f"(d[2]), "+f"(d[3]), "+f"(d[4]), "+f"(d[5]), "+f"(d[6]), "+f"(d[7]), "+f"(d[8]), "+f"(d[9]), "+f"(d[10]), "+f"(d[11]), "+f"(d[12]), "+f"(d[13]), "+f"(d[14]), "+f"(d[15]), "+f"(d[16]), "+f"(d[17]), "+f"(d[18]), "+f"(d[19]), "+f"(d[20]), "+f"(d[21]), "+f"(d[22]), "+f"(d[23]), "+f"(d[24]), "+f"(d[25]), "+f"(d[26]), "+f"(d[27]), "+f"(d[28]), "+f"(d[29]), "+f"(d[30]), "+f"(d[31]), "+f"(d[32]), "+f"(d[33]), "+f"(d[34]), "+f"(d[35])
    : "l"(da), "l"(db), "r"(scale_d), "n"(TA), "n"(TB), "n"(SA));
}
template<int TB, int SA=1> __device__ __forceinline__ void wgmma_rs_n40(float (&d)[20], uint32_t a0, uint32_t a1, uint32_t a2, uint32_t a3, uint64_t db, int scale_d) {
  asm volatile("{\n.reg .pred p;\nsetp.ne.b32 p, %25, 0;\n"
    "wgmma.mma_async.sync.aligned.m64n40k16.f32.bf16.bf16 {%0, %1, %2, %3, %4, %5, %6, %7, %8, %9, %10, %11, %12, %13, %14, %15, %16, %17, %18, %19}, {%20, %21, %22, %23}, %24, p, %27, 1, %26;\n}\n"
    : "+f"(d[0]), "+f"(d[1]), "+f"(d[2]), "+f"(d[3]), "+f"(d[4]), "+f"(d[5]), "+f"(d[6]), "+f"(d[7]), "+f"(d[8]), "+f"(d[9]), "+f"(d[10]), "+f"(d[11]), "+f"(d[12]), "+f"(d[13]), "+f"(d[14]), "+f"(d[15]), "+f"(d[16]), "+f"(d[17]), "+f"(d[18]), "+f"(d[19])
    : "r"(a0), "r"(a1), "r"(a2), "r"(a3), "l"(db), "r"(scale_d), "n"(TB), "n"(SA));
}
template<int TB> __device__ __forceinline__ void wgmma_hrs_n64(uint32_t (&d)[16], uint32_t a0, uint32_t a1, uint32_t a2, uint32_t a3, uint64_t db, int scale_d) {
  asm volatile("{\n.reg .pred p;\nsetp.ne.b32 p, %21, 0;\n"
    "wgmma.mma_async.sync.aligned.m64n64k16.f16.f16.f16 {%0, %1, %2, %3, %4, %5, %6, %7, %8, %9, %10, %11, %12, %13, %14, %15}, {%16, %17, %18, %19}, %20, p, 1, 1, %22;\n}\n"
    : "+r"(d[0]), "+r"(d[1]), "+r"(d[2]), "+r"(d[3]), "+r"(d[4]), "+r"(d[5]), "+r"(d[6]), "+r"(d[7]), "+r"(d[8]), "+r"(d[9]), "+r"(d[10]), "+r"(d[11]), "+r"(d[12]), "+r"(d[13]), "+r"(d[14]), "+r"(d[15])
    : "r"(a0), "r"(a1), "r"(a2), "r"(a3), "l"(db), "r"(scale_d), "n"(TB));
}
template<int TB> __device__ __forceinline__ void wgmma_hrs_n32(uint32_t (&d)[8], uint32_t a0, uint32_t a1, uint32_t a2, uint32_t a3, uint64_t db, int scale_d) {
  asm volatile("{\n.reg .pred p;\nsetp.ne.b32 p, %13, 0;\n"
    "wgmma.mma_async.sync.aligned.m64n32k16.f16.f16.f16 {%0, %1, %2, %3, %4, %5, %6, %7}, {%8, %9, %10, %11}, %12, p, 1, 1, %14;\n}\n"
    : "+r"(d[0]), "+r"(d[1]), "+r"(d[2]), "+r"(d[3]), "+r"(d[4]), "+r"(d[5]), "+r"(d[6]), "+r"(d[7])
    : "r"(a0), "r"(a1), "r"(a2), "r"(a3), "l"(db), "r"(scale_d), "n"(TB));
}

__device__ __align__(128) const uint32_t c_thr[1536] = {
  0x33fb33ff,0xa49c9de4,0x33273352,0xaf2cae76,0x33e233f1,0xa96ca7bd,0x32c432f7,0xb045afdd,0x33b733cf,0xac3eaaf7,0x3250328c,0xb0eab099,
  0x3378339a,0xadbcacff,0x31cd3211,0xb182b137,0x33d033fb,0xaadea46a,0x299e2d17,0xb3e0b396,0x32fb337a,0xafd2adb1,0xa78b1f76,0xb3f2b3ff,
  0x318b3254,0xb1c5b0e5,0xae6bac32,0xb354b3b8,0x2f4230a3,0xb321b285,0xb133b040,0xb215b2c7,0x337c33f2,0xada5a759,0xb179afc8,0xb1d6b2fe,
  0x31463293,0xb204b08e,0xb394b2ba,0xad23b055,0x2b402f4e,0xb3cbb31e,0xb3e4b3f9,0x293ba533,0xac269c52,0xb3bab400,0xb258b357,0x30e02e5f,
  0x330133e5,0xafbda922,0xb3f3b3c9,0x2727ab59,0x2deb314a,0xb36fb200,0xb194b32f,0x31bc2f0a,0xacdb2084,0xb39fb3ff,0xa565aea4,0x33f93347,
  0xb2b6b0db,0xb05ab25c,0x30892c1a,0x329733bc,0x326033d4,0xb0d6aa94,0xb00ab29b,0x32e83084,0x20e82f64,0xb3feb318,0x2d8da597,0x338133f8,
  0xb1fcae48,0xb14fb35c,0x339031b8,0x2d3a3199,0xb3e6b3ae,0x2909ac7b,0x32d133f4,0xb030a6f5,0x319d33bf,0xb1b3ac02,0x2e3ca874,0x335e33ec,
  0xacc32b89,0xb3a3b3c6,0x33f83276,0x25c930b7,0xb3dcb1f8,0xaa01b154,0x30653335,0xb2b0aef4,0xb107b383,0x32392d81,0xafa6214d,0xb307b3fe,
  0x30bc33a5,0xb273acb7,0x33c5311b,0x2ba23229,0xb0cc94b6,0xb267b400,0x30153360,0xb2e1ae31,0xb385b3ab,0x2d76ac93,0xb166a691,0xb1e7b3f5,
  0x22deb06a,0x33fd32ac,0xb337b3da,0x2ee8aa19,0x2f853387,0xb310ad6a,0x322d33fe,0xb1162216,0xb2a9abd3,0xb06fb3c2,0xb07428a6,0xb2a5b3ea,
  0xb111b3e9,0x323128be,0xb30db3c3,0x2f90abba,0x31aa227a,0x31a633fd,0x2e25ad5e,0x33633389,0x2d6a3365,0xb387ae1a,0xa21631aa,0xb3feb1a6,
  0xb3c2af85,0xabd3b310,0xb3eab22d,0x28a6b116,0xa8beb2a9,0x33e9306f,0x2bbab074,0x33c332a5,0x33fd3111,0x227a3231,0x3389330d,0xad5e2f90,
  0x2a63333f,0xb3d7aec6,0xb2a2a1b1,0xb07ab3fe,0xb3f7b158,0x25fbb1f4,0xacb7b38b,0x33a52d52,0x2e0eb025,0x336832d8,0x340030bc,0x14b63273,
  0x323533c0,0xb10c2beb,0xac9330cc,0xb3abb267,0x23433316,0xb3fdaf6f,0xb38eb225,0x2d46b11f,0xb342b29e,0x2ebbb07f,0x31e3aa7c,0x316b33d6,
  0x3264a6c3,0x30d133f5,0x2c0233ac,0xb3bfac87,0x28f0336a,0xb3e7ae02,0xb3c6b19d,0x2b89b1b3,0xa59732e8,0xb3f8b00a,0xaccfb3ed,0x33a1285b,
  0xb1b8b381,0x3199ad8d,0x336c31df,0xadf73170,0x33f42d3a,0x26f53390,0xb30423a7,0xafb2b3fc,0xb05f3030,0xb2b3b2d1,0x29e8b27a,0x33dd30b2,
  0xab5932b6,0xb3c9b05a,0x30adb089,0x327e3297,0xaf0ab3f3,0x332fa727,0x240633b0,0xb3fcac6f,0x33473194,0xaea431bc,0xb174b359,0x31daae54,
  0xb3bca565,0xac1ab3f9,0x33ee2f59,0xa842331b,0xaddf3281,0xb371b0a8,0x34002b40,0x1c5233cb,0xa759b3ef,0x33f22829,0xb2fe2c26,0xafc8b3ba,
  0x308e337c,0xb2932da5,0x3055b179,0x32ba31d6,0xb31eb146,0x2f4eb204,0xa5333394,0xb3f9ad23,0xaff33249,0xb2f1b0f3,0x30e532fb,0xb2542fd2,
  0x2b28b373,0x33cc2dd4,0xb285b18b,0x30a3b1c5,0x246a33fa,0xb3fba500,0x33962f42,0xad173321,0xadb1b3d0,0x337aaade,0xb3ffa99e,0x1f76b3e0,
  0xb0ee320d,0xb24db13c,0xac4b3398,0xb3b5ad0b,0x304ab289,0x32c1309e,0x2985b3ce,0x33e12b0f,0xaf3732f4,0xb324afe8,0xa4ce33f0,0xb3faa7ef,
  0x2dc8b34f,0x33762e82,0x9de4b3ff,0x33ff1ead,0xb1c931cd,0xb186b182,0xb3762e82,0xadc8b34f,0x324db13c,0x30ee320d,0x33b5ad0b,0x2c4b3398,
  0xb2c1309e,0xb04ab289,0xb3e12b0f,0xa985b3ce,0x3324afe8,0x2f3732f4,0x33faa7ef,0x24ce33f0,0xb285318b,0xb0a3b1c5,0xb2c7ae6b,0x3040b354,
  0x3396af42,0x2d173321,0x31413133,0xb2093215,0xb3ff299e,0x9f76b3e0,0xae8db2bd,0x334cb050,0x33b8278b,0xac3233f2,0x281033b3,0xb3ef2c57,
  0xb31e3146,0xaf4eb204,0xa533b394,0x33f9ad23,0x3400ab40,0x9c5233cb,0xae5f33e4,0xb357a93b,0xb2feac26,0x2fc8b3ba,0x3245b258,0x30f830e0,
  0x30553179,0xb2ba31d6,0xb3df2e99,0xa9b6b34a,0xb39230fd,0xad2fb241,0x3200b301,0x314a2fbd,0x337f1b11,0xad993400,0xb3ff2deb,0xa084b36f,
  0xb005b129,0x32ebb21d,0x325c2cdb,0xb0db339f,0xa92233de,0xb3e529cf,0xab59b2b6,0x33c9b05a,0xb3dd30b2,0xa9e8b27a,0x33d4ab71,0xaa9433c8,
  0x32212c0e,0xb12433bd,0xaf64b0d6,0x3318b260,0x197fb345,0x3400aeaf,0xae4833fe,0xb35c20e8,0xb23d3332,0xb102aeff,0x33aeb14f,0x2c7b31fc,
  0xb3fe3065,0xa14db2b0,0x2ebb307f,0xb342329e,0x300f2fa6,0xb2e53307,0x30d1b3f5,0x326426c3,0x302ab400,0x32d517db,0xb3e72e02,0x28f0b36a,
  0xb3fd2f6f,0x2343b316,0x2d46311f,0xb38e3225,0xb3f53015,0x2691b2e1,0xaf9b33eb,0xb30a288d,0x2a193166,0xb3da31e7,0x33d7aec6,0xaa63333f,
  0x3313b337,0x2f7a2ee8,0xa5fbb1f4,0x33f7b158,0xb1a1a8d7,0x31afb3e8,0xb36832d8,0xae0eb025,0xb3c22f85,0x2bd3b310,0xb3ea322d,0xa8a6b116,
  0xa8be32a9,0xb3e9306f,0x2bba3074,0xb3c332a5,0x33fdb111,0xa27a3231,0x3389b30d,0x2d5e2f90,0xa216b1aa,0x33feb1a6,0xaed2ae25,0x333db363,
  0xb3652edd,0x2e1ab33a,0xb1aa227a,0x31a6b3fd,0xaf853387,0xb3102d6a,0xb22d33fe,0xb116a216,0x32a9abd3,0xb06f33c2,0x307428a6,0xb2a533ea,
  0x3111b3e9,0x3231a8be,0x330db3c3,0x2f902bba,0xb2e12e31,0x3015b360,0x288db1a1,0x33ebb1af,0xb1e733f5,0xb1662691,0xb33f2f9b,0x2ec6b30a,
  0x2ee82a19,0xb33733da,0xb15833d7,0xb1f42a63,0x33e8b313,0x28d72f7a,0x302525fb,0xb2d833f7,0xb2392d81,0x3107b383,0x3307b3fe,0x2fa6214d,
  0xb35e33ec,0xae3ca874,0x97dbb00f,0x3400b2e5,0xa5c930b7,0xb3f83276,0xb316302a,0x2f6fb2d5,0x32b0aef4,0xb0653335,0xb29e33fd,0xb07f2343,
  0xb1702ccf,0x31dfb3a1,0x3345b124,0xaeaf3221,0xb3fc336c,0xa3a7adf7,0x3332b400,0x2eff997f,0xb0b23304,0xb27a2fb2,0x2b71b102,0x33c8b23d,
  0x2c0e29e8,0xb3bd33dd,0xb0d62a94,0x3260b3d4,0xb0892c1a,0x3297b3bc,0x2aad2842,0xb3d333ee,0xb3b0327e,0x2c6fb0ad,0x3241b035,0xb0fd32ce,
  0xb35933fc,0xae542406,0x3400b392,0x1b112d2f,0xaf5931da,0xb31b3174,0x321db37f,0x3129ad99,0xaf152ac6,0x332cb3d2,0xb1463293,0xb204308e,
  0xb281312e,0x30a8b219,0xab402f4e,0xb3cb331e,0xb3ef3371,0x2829addf,0x2c269c52,0xb3ba3400,0xb37c33f2,0xada52759,0x3179afc8,0xb1d632fe,
  0xacf32953,0x339cb3e3,0xb3fa33cc,0x2500ab28,0xb0942f21,0x3290b32a,0xb3d033fb,0xaade246a,0xb249317d,0x30f3b1d2,0xb2fb337a,0xafd22db1,
  0xb37332f1,0x2dd4aff3,0xb18b3254,0xb1c530e5,0xa96c27bd,0x33e2b3f1,0xb0452fdd,0x32c4b2f7,0xac3e2af7,0x33b7b3cf,0xb0ea3099,0x3250b28c,
  0xadbc2cff,0x3378b39a,0xb1823137,0x31cdb211,0xaf2c2e76,0x3327b352,0xb20d31c9,0x313cb186,0x313c3186,0xb20db1c9,0x2d0b2dc8,0xb398b376,
  0x309e30ee,0xb289b24d,0x2b0f2c4b,0xb3ceb3b5,0x2fe8304a,0xb2f4b2c1,0x27ef2985,0xb3f0b3e1,0x2e822f37,0xb34fb324,0x1ead24ce,0xb3ffb3fa,
  0xb2bdb209,0xb050b141,0xb290b32a,0x30942f21,0xb3b3b34c,0xac57ae8d,0xb0f3b1d2,0x3249317d,0xb400b3ef,0x1d1ba810,0xadd4aff3,0x337332f1,
  0xb39cb3e3,0x2cf32953,0xa500ab28,0x33fa33cc,0xae99b0f8,0x334a3245,0x33ff33b2,0x201f2c63,0x2438a9b6,0x33fc33df,0x332c33d2,0xaf15aac6,
  0x303a2ce7,0x32cb339e,0x30a83219,0xb281b12e,0x32ee31c0,0x2ffe3190,0x28292ddf,0xb3efb371,0x33b0327e,0x2c6f30ad,0xb241b035,0xb0fdb2ce,
  0x335933fc,0xae54a406,0xb400b392,0x1b11ad2f,0x2f5931da,0xb31bb174,0xb21db37f,0x31292d99,0xaaad2842,0xb3d3b3ee,0xa9cfb005,0x33de32eb,
  0x285b305f,0xb3edb2b3,0x2c0ea9e8,0x33bd33dd,0xb170accf,0xb1dfb3a1,0x33453124,0x2eaf3221,0xb3fcb36c,0x23a7adf7,0x33323400,0xaeff997f,
  0xb0b2b304,0x327a2fb2,0x2b713102,0xb3c8b23d,0xb400b2e5,0x17dbb00f,0x2e023264,0xb36ab0d1,0xaf6fb2d5,0x3316302a,0xb11fa8f0,0xb225b3e7,
  0x307f2343,0x329e33fd,0xb3d6b38e,0x2a7cad46,0x33f53342,0xa6c32ebb,0xac87b1e3,0x33ac316b,0x28d7af7a,0x33e83313,0xb2d8b3f7,0x3025a5fb,
  0x33eb31af,0x288d31a1,0x2bebae0e,0x33c03368,0x2ec6330a,0xb33faf9b,0x33fe3235,0x21b1310c,0xb1f4aa63,0xb158b3d7,0x2d5232a2,0xb38bb07a,
  0x33a7333d,0xacab2ed2,0x33f63162,0x262d31eb,0xaa4b301a,0xb3d8b2de,0x2a32326b,0xb3d9b0c7,0xb3f6b26f,0x265fb0c1,0xb3a9b020,0xac9fb2db,
  0x0e48b15d,0x340031f0,0xae1ab33a,0x33652edd,0xaed22e25,0xb33db363,0xb1eb0e48,0xb162b400,0xb2deb3a7,0x301aacab,0xb0c7b3f6,0x326b262d,
  0x30c1aa4b,0x326f33d8,0x32db2a32,0x302033d9,0x31f033f6,0xb15d265f,0x2edd33a9,0xb33aac9f,0xb2acb385,0x306aad76,0x2a19b166,0x33da31e7,
  0x3229a2de,0x311b33fd,0x33133337,0xaf7a2ee8,0x2e3133c5,0xb360aba2,0xb1a128d7,0xb1afb3e8,0xb3f5b015,0xa691b2e1,0xaf9bb3eb,0x330a288d,
  0x3154acc3,0x31f833a3,0x2ef433f8,0xb335a5c9,0x2d8133dc,0xb383aa01,0xb3feb065,0x214db2b0,0xb3ecb107,0x2874b239,0x300fafa6,0x32e53307,
  0x30b7ae3c,0x3276335e,0x302a3400,0xb2d517db,0x312433bd,0xb2212c0e,0xb318b260,0x2f64b0d6,0xb400aeaf,0x997fb345,0x335c20e8,0x2e4833fe,
  0x3102aeff,0x323d3332,0xac7b31fc,0xb3aeb14f,0x2a9433c8,0xb3d4ab71,0xb084b3e6,0x329ba909,0xb2ce2aad,0xb035b3d3,0x33e529cf,0x292233de,
  0x2d2fb241,0x339230fd,0xb14a2fbd,0xb200b301,0x2d993400,0xb37f1b11,0x2084b36f,0x33ff2deb,0xb2ebb21d,0x3005b129,0x30db339f,0xb25c2cdb,
  0xae5fb3e4,0x3357a93b,0xb190303a,0xb1c0b2cb,0x32453258,0xb0f830e0,0x2c63b2ee,0x33b22ffe,0xb3dfae99,0x29b6b34a,0x2ac633ff,0xb3d2a01f,
  0x339ea438,0x2ce733fc,0xb12eb32c,0x3219af15,0x33b8a78b,0x2c3233f2,0x2810b3b3,0x33ef2c57,0xb2c72e6b,0xb040b354,0x29533400,0xb3e31d1b,
  0x3141b133,0x32093215,0xaf21b39c,0x332aacf3,0xae8d32bd,0xb34cb050,0x317d3290,0xb1d23094,0x27bd33fb,0xb3f1249c,0x2fdd3327,0xb2f72f2c,
  0xaaf7b3e2,0x33cfa96c,0xb099b2c4,0x328cb045,0x2cff33b7,0xb39a2c3e,0x31373250,0xb21130ea,0xae76b378,0x3352adbc,0xb1c9b1cd,0x3186b182,
  0xb3ff1ead,0x1de4b3ff,0xb352adbc,0x2e76b378,0x33f1249c,0xa7bd33fb,0x32f72f2c,0xafdd3327,0xb3cfa96c,0x2af7b3e2,0xb28cb045,0x3099b2c4,
  0x339a2c3e,0xacff33b7,0x321130ea,0xb1373250,0x2953b400,0x33e31d1b,0x33ccadd4,0x2b283373,0xaf21339c,0xb32aacf3,0xb3fb2500,0x246ab3fa,
  0x317db290,0x31d23094,0x337a2ade,0xadb133d0,0xb2f130f3,0xaff3b249,0xb254afd2,0x30e5b2fb,0x339e2438,0xace733fc,0xb12e332c,0xb219af15,
  0xb190b03a,0x31c0b2cb,0x3371b0a8,0x2ddf3281,0x2c6332ee,0xb3b22ffe,0xb3f22829,0x2759b3ef,0x2ac6b3ff,0x33d2a01f,0x32932da5,0xb08e337c,
  0xaf0a33f3,0xb32fa727,0x2406b3b0,0x33fcac6f,0x3347b194,0x2ea431bc,0xb1743359,0xb1daae54,0xb3bc2565,0x2c1ab3f9,0x33eeaf59,0x2842331b,
  0x30ad3089,0xb27e3297,0xb2ceaaad,0x3035b3d3,0xb29ba909,0x3084b3e6,0x305f3030,0xb2b332d1,0x259732e8,0xb3f8300a,0x2ccfb3ed,0x33a1a85b,
  0x31b8b381,0x31992d8d,0xb36c31df,0xadf7b170,0xb3f42d3a,0x26f5b390,0x330423a7,0xafb233fc,0x316bb3d6,0x31e32a7c,0xb3832a01,0x2d81b3dc,
  0xb3bf2c87,0x2c02b3ac,0x28743239,0xb3ec3107,0x2b8931b3,0xb3c6319d,0x3276b35e,0x30b72e3c,0x31f8b3a3,0x31542cc3,0xb33525c9,0x2ef4b3f8,
  0x310c2beb,0xb23533c0,0x33abb267,0x2c9330cc,0x307ab3fe,0x32a2a1b1,0xb06aad76,0x32acb385,0xb3a52d52,0x2cb7b38b,0xb11b33fd,0xb229a2de,
  0x94b63273,0xb40030bc,0x3360aba2,0xae3133c5,0xb2de33a7,0xb01aacab,0xb0c733f6,0xb26b262d,0x30c12a4b,0xb26f33d8,0x32dbaa32,0xb02033d9,
  0x31f0b3f6,0x315d265f,0x2eddb3a9,0x333aac9f,0xb1eb8e48,0x3162b400,0xb3872e1a,0x2d6ab365,0xae25ad5e,0x3363b389,0x8e48b15d,0x3400b1f0,
  0xb3a7333d,0xacabaed2,0xb3f63162,0x262db1eb,0x2a4b301a,0xb3d832de,0xaa32326b,0xb3d930c7,0x33f6b26f,0x265f30c1,0x33a9b020,0xac9f32db,
  0x33c0b368,0x2beb2e0e,0x30cc94b6,0xb2673400,0x21b1b10c,0x33feb235,0x3385b3ab,0x2d762c93,0xb38b307a,0x2d52b2a2,0xa2deb06a,0x33fdb2ac,
  0xb0bc33a5,0xb2732cb7,0xb3c5311b,0x2ba2b229,0x26c32ebb,0xb3f53342,0xb3ac316b,0x2c87b1e3,0x336ab0d1,0xae023264,0xb19d33bf,0xb1b32c02,
  0x3225b3e7,0x311fa8f0,0x2cc32b89,0xb3a333c6,0xaa7cad46,0x33d6b38e,0x33dcb1f8,0xaa013154,0xb3fe3318,0x20e8af64,0x3381b3f8,0x2d8d2597,
  0xb14f335c,0xb1fc2e48,0x2d3ab199,0x3390b1b8,0x29092c7b,0xb3e633ae,0xb03026f5,0x32d1b3f4,0x32e8b084,0xb00a329b,0xb3ed32b3,0x285bb05f,
  0x29cfb005,0x33deb2eb,0xb05a325c,0xb2b630db,0xafbd2922,0x3301b3e5,0x27272b59,0xb3f333c9,0xb36f3200,0x2debb14a,0x31bcaf0a,0xb194332f,
  0xb39f33ff,0xacdba084,0x33f9b347,0xa5652ea4,0x3394b2ba,0xad233055,0xa438a9b6,0x33fcb3df,0x33e4b3f9,0x293b2533,0xb03a2ce7,0x32cbb39e,
  0x3258b357,0x30e0ae5f,0xb2ee31c0,0x2ffeb190,0x2e99b0f8,0x334ab245,0xb3ff33b2,0x201fac63,0xaf4230a3,0xb3213285,0x3133b040,0xb21532c7,
  0xa99e2d17,0xb3e03396,0x32bdb209,0xb0503141,0x278b1f76,0xb3f233ff,0x33b3b34c,0xac572e8d,0x2e6bac32,0xb35433b8,0x3400b3ef,0x1d1b2810,
  0xb289324d,0x309eb0ee,0xb3ce33b5,0x2b0fac4b,0xb2f432c1,0x2fe8b04a,0xb3f033e1,0x27efa985,0xb34f3324,0x2e82af37,0xb3ff33fa,0x1eada4ce,
  0xb3983376,0x2d0badc8,0xb3fb33ff,0xa49c1de4,0x351c35f6,0xac93a617,0xb8a3b93c,0x308d2a16,0x32f43448,0xb160afa5,0xb6a4b7fe,0x353a3389,
  0x2fa53160,0xb448b2f4,0xb389b53a,0x37fe36a4,0x26172c93,0xb5f6b51c,0xaa16b08d,0x393c38a3,0x34c3358c,0xac47a5b2,0xb85fb8f3,0x304229b1,
  0x327e33fd,0xb106af26,0xb63cb785,0x34e7330f,0x2f263106,0xb3fdb27e,0xb30fb4e7,0x3785363c,0x25b22c47,0xb58cb4c3,0xa9b1b042,0x38f3385f,
  0x346a3523,0xabf6a54d,0xb81ab8a8,0x2fef294d,0x3209336b,0xb0acaea7,0xb5d4b70a,0x34933294,0x2ea730ac,0xb36bb209,0xb294b493,0x370a35d4,
  0x254d2bf6,0xb523b46a,0xa94dafef,0x38a8381a,0x341334bc,0xab5fa4e9,0xb7a6b85a,0x2f5928e8,0x319432da,0xb052ae28,0xb56ab68d,0x343e3219,
  0x2e283052,0xb2dab194,0xb219b43e,0x368d356a,0x24e92b5f,0xb4bcb413,0xa8e8af59,0x385a37a6,0x33783456,0xaac8a484,0xb715b80a,0x2ec32884,
  0x3120324a,0xaff2ada9,0xb4ffb60e,0x33d3319e,0x2da92ff2,0xb24ab120,0xb19eb3d3,0x360e34ff,0x24842ac8,0xb456b378,0xa884aec3,0x380a3715,
  0x32cd33e3,0xaa31a420,0xb682b76f,0x2e2d281f,0x30ac31bb,0xaf3fad2a,0xb493b58d,0x33283122,0x2d2a2f3f,0xb1bbb0ac,0xb122b328,0x358d3493,
  0x24202a31,0xb3e3b2cd,0xa81fae2d,0x376f3682,0x3223331c,0xa999a376,0xb5ebb6c6,0x2d972776,0x3039312d,0xae8dacac,0xb426b50b,0x327c30a6,
  0x2cac2e8d,0xb12db039,0xb0a6b27c,0x350b3426,0x23762999,0xb31cb223,0xa776ad97,0x36c635eb,0x317a3257,0xa902a2ad,0xb552b61a,0x2d0026ad,
  0x2f8c309f,0xaddcac2e,0xb371b487,0x31cf3029,0x2c2e2ddc,0xb09faf8c,0xb029b1cf,0x34873371,0x22ad2902,0xb257b17a,0xa6adad00,0x361a3552,
  0x30d23194,0xa86ba1e4,0xb4b7b56a,0x2c6a25e4,0x2ea73012,0xad2aab5f,0xb294b402,0x31222f59,0x2b5f2d2a,0xb012aea7,0xaf59b122,0x34023294,
  0x21e4286b,0xb194b0d2,0xa5e4ac6a,0x356a34b7,0x302c30d2,0xa7a9a11b,0xb41ab4b7,0x2ba7251b,0x2dc22f0c,0xac79aa63,0xb1b6b2f7,0x30742e5f,
  0x2a632c79,0xaf0cadc2,0xae5fb074,0x32f731b6,0x211b27a9,0xb0d2b02c,0xa51baba7,0x34b7341a,0x2f0c3012,0xa67ba052,0xb2f7b402,0x2a7a2452,
  0x2cde2df5,0xab91a967,0xb0d7b1e8,0x2f8b2d65,0x29672b91,0xadf5acde,0xad65af8b,0x31e830d7,0x2052267b,0xb012af0c,0xa452aa7a,0x340232f7,
  0x2dc22ea7,0xa54d9f12,0xb1b6b294,0x294d2311,0x2bf62cde,0xaa31a86b,0xafefb0d7,0x2e2d2c6a,0x286b2a31,0xacdeabf6,0xac6aae2d,0x30d72fef,
  0x1f12254d,0xaea7adc2,0xa311a94d,0x329431b6,0x2c792d2a,0xa4209d7f,0xb074b122,0x281f217f,0x2a312b91,0xa8d0a6e0,0xae2daf8b,0x2cce2ade,
  0x26e028d0,0xab91aa31,0xaadeacce,0x2f8b2e2d,0x1d7f2420,0xad2aac79,0xa17fa81f,0x31223074,0x2a632b5f,0xa1e49bdb,0xae5faf59,0x25e41fdb,
  0x286b2967,0xa6e0a4e9,0xac6aad65,0x2ade28e8,0x24e926e0,0xa967a86b,0xa8e8aade,0x2d652c6a,0x1bdb21e4,0xab5faa63,0x9fdba5e4,0x2f592e5f,
  0x27a9286b,0x9f1298b6,0xaba7ac6a,0x23111cb6,0x254d267b,0xa420a1e4,0xa94daa7a,0x281f25e4,0x21e42420,0xa67ba54d,0xa5e4a81f,0x2a7a294d,
  0x18b61f12,0xa86ba7a9,0x9cb6a311,0x2c6a2ba7,0x211b21e4,0x98b69248,0xa51ba5e4,0x1cb61648,0x1f122052,0x9d7f9bdb,0xa311a452,0x217f1fdb,
  0x1bdb1d7f,0xa0529f12,0x9fdba17f,0x24522311,0x124818b6,0xa1e4a11b,0x96489cb6,0x25e4251b,0xa11ba1e4,0x18b61248,0x251b25e4,0x9cb69648,
  0x9f12a052,0x1d7f1bdb,0x23112452,0xa17f9fdb,0x9bdb9d7f,0x20521f12,0x1fdb217f,0xa452a311,0x924898b6,0x21e4211b,0x16481cb6,0xa5e4a51b,
  0xa7a9a86b,0x1f1218b6,0x2ba72c6a,0xa3119cb6,0xa54da67b,0x242021e4,0x294d2a7a,0xa81fa5e4,0xa1e4a420,0x267b254d,0x25e4281f,0xaa7aa94d,
  0x98b69f12,0x286b27a9,0x1cb62311,0xac6aaba7,0xaa63ab5f,0x21e41bdb,0x2e5f2f59,0xa5e49fdb,0xa86ba967,0x26e024e9,0x2c6a2d65,0xaadea8e8,
  0xa4e9a6e0,0x2967286b,0x28e82ade,0xad65ac6a,0x9bdba1e4,0x2b5f2a63,0x1fdb25e4,0xaf59ae5f,0xac79ad2a,0x24201d7f,0x30743122,0xa81fa17f,
  0xaa31ab91,0x28d026e0,0x2e2d2f8b,0xacceaade,0xa6e0a8d0,0x2b912a31,0x2ade2cce,0xaf8bae2d,0x9d7fa420,0x2d2a2c79,0x217f281f,0xb122b074,
  0xadc2aea7,0x254d1f12,0x31b63294,0xa94da311,0xabf6acde,0x2a31286b,0x2fef30d7,0xae2dac6a,0xa86baa31,0x2cde2bf6,0x2c6a2e2d,0xb0d7afef,
  0x9f12a54d,0x2ea72dc2,0x2311294d,0xb294b1b6,0xaf0cb012,0x267b2052,0x32f73402,0xaa7aa452,0xacdeadf5,0x2b912967,0x30d731e8,0xaf8bad65,
  0xa967ab91,0x2df52cde,0x2d652f8b,0xb1e8b0d7,0xa052a67b,0x30122f0c,0x24522a7a,0xb402b2f7,0xb02cb0d2,0x27a9211b,0x341a34b7,0xaba7a51b,
  0xadc2af0c,0x2c792a63,0x31b632f7,0xb074ae5f,0xaa63ac79,0x2f0c2dc2,0x2e5f3074,0xb2f7b1b6,0xa11ba7a9,0x30d2302c,0x251b2ba7,0xb4b7b41a,
  0xb0d2b194,0x286b21e4,0x34b7356a,0xac6aa5e4,0xaea7b012,0x2d2a2b5f,0x32943402,0xb122af59,0xab5fad2a,0x30122ea7,0x2f593122,0xb402b294,
  0xa1e4a86b,0x319430d2,0x25e42c6a,0xb56ab4b7,0xb17ab257,0x290222ad,0x3552361a,0xad00a6ad,0xaf8cb09f,0x2ddc2c2e,0x33713487,0xb1cfb029,
  0xac2eaddc,0x309f2f8c,0x302931cf,0xb487b371,0xa2ada902,0x3257317a,0x26ad2d00,0xb61ab552,0xb223b31c,0x29992376,0x35eb36c6,0xad97a776,
  0xb039b12d,0x2e8d2cac,0x3426350b,0xb27cb0a6,0xacacae8d,0x312d3039,0x30a6327c,0xb50bb426,0xa376a999,0x331c3223,0x27762d97,0xb6c6b5eb,
  0xb2cdb3e3,0x2a312420,0x3682376f,0xae2da81f,0xb0acb1bb,0x2f3f2d2a,0x3493358d,0xb328b122,0xad2aaf3f,0x31bb30ac,0x31223328,0xb58db493,
  0xa420aa31,0x33e332cd,0x281f2e2d,0xb76fb682,0xb378b456,0x2ac82484,0x3715380a,0xaec3a884,0xb120b24a,0x2ff22da9,0x34ff360e,0xb3d3b19e,
  0xada9aff2,0x324a3120,0x319e33d3,0xb60eb4ff,0xa484aac8,0x34563378,0x28842ec3,0xb80ab715,0xb413b4bc,0x2b5f24e9,0x37a6385a,0xaf59a8e8,
  0xb194b2da,0x30522e28,0x356a368d,0xb43eb219,0xae28b052,0x32da3194,0x3219343e,0xb68db56a,0xa4e9ab5f,0x34bc3413,0x28e82f59,0xb85ab7a6,
  0xb46ab523,0x2bf6254d,0x381a38a8,0xafefa94d,0xb209b36b,0x30ac2ea7,0x35d4370a,0xb493b294,0xaea7b0ac,0x336b3209,0x32943493,0xb70ab5d4,
  0xa54dabf6,0x3523346a,0x294d2fef,0xb8a8b81a,0xb4c3b58c,0x2c4725b2,0x385f38f3,0xb042a9b1,0xb27eb3fd,0x31062f26,0x363c3785,0xb4e7b30f,
  0xaf26b106,0x33fd327e,0x330f34e7,0xb785b63c,0xa5b2ac47,0x358c34c3,0x29b13042,0xb8f3b85f,0xb51cb5f6,0x2c932617,0x38a3393c,0xb08daa16,
  0xb2f4b448,0x31602fa5,0x36a437fe,0xb53ab389,0xafa5b160,0x344832f4,0x3389353a,0xb7feb6a4,0xa617ac93,0x35f6351c,0x2a16308d,0xb93cb8a3,
};
__device__ __align__(128) const uint32_t c_img[2560] = {
  0x326d31ed,0x333b32dd,0x33c33388,0x33fe33ea,0x33c331ed,0x31ed33c3,0xa8b22d64,0xb33bb0c4,0x33ea31ed,0xad64301d,0xb2ddb388,0x315fa8b2,
  0x32dd31ed,0xb3feabc6,0x326dad64,0xad64326d,0x30c431ed,0xaed7b2dd,0x2bc63388,0xa248b3ea,0x2bc631ed,0x315fb3c3,0xb3ea2d64,0x2ed730c4,
  0xa8b231ed,0x3388b01d,0x301db388,0xb1ed28b2,0xb01d31ed,0x22482bc6,0x30c4ad64,0x3388b26d,0x33ea33fe,0x338833c3,0x32dd333b,0x31ed326d,
  0xb2ddb3fe,0xa248b01d,0x326d2ed7,0x338833ea,0x30c433fe,0xb33babc6,0xabc6b33b,0x33fe30c4,0xabc6b3fe,0x31ed32dd,0xb3eaaed7,0x333ba8b2,
  0xa8b233fe,0x2d64b3c3,0xb01d333b,0x315fb26d,0x301db3fe,0xb3fe301d,0x30c42ed7,0x2d64b3ea,0xb26d33fe,0x2ed72bc6,0x33c3b33b,0xa248b0c4,
  0x33c3b3fe,0x315fb2dd,0x28b2aed7,0xaed728b2,0xb0c4b15f,0xaed7b01d,0xabc6ad64,0xa248a8b2,0xabc6b15f,0x315f2bc6,0x33ea3388,0x2ed7326d,
  0x28b2b15f,0x338832dd,0xb01d2d64,0xb1edb3ea,0x301db15f,0x224833c3,0xb0c4b388,0x338830c4,0x326db15f,0xb33b301d,0x33c3ad64,0xb3fe28b2,
  0x33c3b15f,0xb1edabc6,0xa8b23388,0x333bb26d,0x33eab15f,0x2d64b2dd,0xb2dd2d64,0xb15f33ea,0x32ddb15f,0x33feb3c3,0x326db388,0x2d64b0c4,
  0x28b22248,0x2d642bc6,0x301d2ed7,0x315f30c4,0xb01da248,0xb3feb2dd,0xb0c4b33b,0x2d64a8b2,0x326d2248,0x2ed733c3,0xb3c3aed7,0xa248b26d,
  0xb3c3a248,0x315fb01d,0xa8b2333b,0xaed7b3ea,0x33ea2248,0xb388abc6,0x32dd2ed7,0xb1edb0c4,0xb2dda248,0x224832dd,0x326db33b,0xb38828b2,
  0x30c42248,0x333bb3c3,0xabc6aed7,0xb3fe326d,0xabc6a248,0xb1ed301d,0xb3ea333b,0xb33b33ea,0xb26d31ed,0xb33b32dd,0xb3c33388,0xb3fe33ea,
  0xb3c331ed,0xb1ed33c3,0x28b22d64,0x333bb0c4,0xb3ea31ed,0x2d64301d,0x32ddb388,0xb15fa8b2,0xb2dd31ed,0x33feabc6,0xb26dad64,0x2d64326d,
  0xb0c431ed,0x2ed7b2dd,0xabc63388,0x2248b3ea,0xabc631ed,0xb15fb3c3,0x33ea2d64,0xaed730c4,0x28b231ed,0xb388b01d,0xb01db388,0x31ed28b2,
  0x301d31ed,0xa2482bc6,0xb0c4ad64,0xb388b26d,0xb3ea33fe,0xb38833c3,0xb2dd333b,0xb1ed326d,0x32ddb3fe,0x2248b01d,0xb26d2ed7,0xb38833ea,
  0xb0c433fe,0x333babc6,0x2bc6b33b,0xb3fe30c4,0x2bc6b3fe,0xb1ed32dd,0x33eaaed7,0xb33ba8b2,0x28b233fe,0xad64b3c3,0x301d333b,0xb15fb26d,
  0xb01db3fe,0x33fe301d,0xb0c42ed7,0xad64b3ea,0x326d33fe,0xaed72bc6,0xb3c3b33b,0x2248b0c4,0xb3c3b3fe,0xb15fb2dd,0xa8b2aed7,0x2ed728b2,
  0x30c4b15f,0x2ed7b01d,0x2bc6ad64,0x2248a8b2,0x2bc6b15f,0xb15f2bc6,0xb3ea3388,0xaed7326d,0xa8b2b15f,0xb38832dd,0x301d2d64,0x31edb3ea,
  0xb01db15f,0xa24833c3,0x30c4b388,0xb38830c4,0xb26db15f,0x333b301d,0xb3c3ad64,0x33fe28b2,0xb3c3b15f,0x31edabc6,0x28b23388,0xb33bb26d,
  0xb3eab15f,0xad64b2dd,0x32dd2d64,0x315f33ea,0xb2ddb15f,0xb3feb3c3,0xb26db388,0xad64b0c4,0xa8b22248,0xad642bc6,0xb01d2ed7,0xb15f30c4,
  0x301da248,0x33feb2dd,0x30c4b33b,0xad64a8b2,0xb26d2248,0xaed733c3,0x33c3aed7,0x2248b26d,0x33c3a248,0xb15fb01d,0x28b2333b,0x2ed7b3ea,
  0xb3ea2248,0x3388abc6,0xb2dd2ed7,0x31edb0c4,0x32dda248,0xa24832dd,0xb26db33b,0x338828b2,0xb0c42248,0xb33bb3c3,0x2bc6aed7,0x33fe326d,
  0x2bc6a248,0x31ed301d,0x33ea333b,0x333b33ea,0x30c4315f,0x2ed7301d,0x2bc62d64,0x224828b2,0x2bc6315f,0xb15fabc6,0xb3eab388,0xaed7b26d,
  0xa8b2315f,0xb388b2dd,0x301dad64,0x31ed33ea,0xb01d315f,0xa248b3c3,0x30c43388,0xb388b0c4,0xb26d315f,0x333bb01d,0xb3c32d64,0x33fea8b2,
  0xb3c3315f,0x31ed2bc6,0x28b2b388,0xb33b326d,0xb3ea315f,0xad6432dd,0x32ddad64,0x315fb3ea,0xb2dd315f,0xb3fe33c3,0xb26d3388,0xad6430c4,
  0xa8b2a248,0xad64abc6,0xb01daed7,0xb15fb0c4,0x301d2248,0x33fe32dd,0x30c4333b,0xad6428b2,0xb26da248,0xaed7b3c3,0x33c32ed7,0x2248326d,
  0x33c32248,0xb15f301d,0x28b2b33b,0x2ed733ea,0xb3eaa248,0x33882bc6,0xb2ddaed7,0x31ed30c4,0x32dd2248,0xa248b2dd,0xb26d333b,0x3388a8b2,
  0xb0c4a248,0xb33b33c3,0x2bc62ed7,0x33feb26d,0x2bc62248,0x31edb01d,0x33eab33b,0x333bb3ea,0x326d31ed,0x333b32dd,0x33c33388,0x33fe33ea,
  0x33c331ed,0x31ed33c3,0xa8b22d64,0xb33bb0c4,0x33ea31ed,0xad64301d,0xb2ddb388,0x315fa8b2,0x32dd31ed,0xb3feabc6,0x326dad64,0xad64326d,
  0x30c431ed,0xaed7b2dd,0x2bc63388,0xa248b3ea,0x2bc631ed,0x315fb3c3,0xb3ea2d64,0x2ed730c4,0xa8b231ed,0x3388b01d,0x301db388,0xb1ed28b2,
  0xb01d31ed,0x22482bc6,0x30c4ad64,0x3388b26d,0x33ea33fe,0x338833c3,0x32dd333b,0x31ed326d,0xb2ddb3fe,0xa248b01d,0x326d2ed7,0x338833ea,
  0x30c433fe,0xb33babc6,0xabc6b33b,0x33fe30c4,0xabc6b3fe,0x31ed32dd,0xb3eaaed7,0x333ba8b2,0xa8b233fe,0x2d64b3c3,0xb01d333b,0x315fb26d,
  0x301db3fe,0xb3fe301d,0x30c42ed7,0x2d64b3ea,0xb26d33fe,0x2ed72bc6,0x33c3b33b,0xa248b0c4,0x33c3b3fe,0x315fb2dd,0x28b2aed7,0xaed728b2,
  0xb0c4315f,0xaed7301d,0xabc62d64,0xa24828b2,0xabc6315f,0x315fabc6,0x33eab388,0x2ed7b26d,0x28b2315f,0x3388b2dd,0xb01dad64,0xb1ed33ea,
  0x301d315f,0x2248b3c3,0xb0c43388,0x3388b0c4,0x326d315f,0xb33bb01d,0x33c32d64,0xb3fea8b2,0x33c3315f,0xb1ed2bc6,0xa8b2b388,0x333b326d,
  0x33ea315f,0x2d6432dd,0xb2ddad64,0xb15fb3ea,0x32dd315f,0x33fe33c3,0x326d3388,0x2d6430c4,0x28b2a248,0x2d64abc6,0x301daed7,0x315fb0c4,
  0xb01d2248,0xb3fe32dd,0xb0c4333b,0x2d6428b2,0x326da248,0x2ed7b3c3,0xb3c32ed7,0xa248326d,0xb3c32248,0x315f301d,0xa8b2b33b,0xaed733ea,
  0x33eaa248,0xb3882bc6,0x32ddaed7,0xb1ed30c4,0xb2dd2248,0x2248b2dd,0x326d333b,0xb388a8b2,0x30c4a248,0x333b33c3,0xabc62ed7,0xb3feb26d,
  0xabc62248,0xb1edb01d,0xb3eab33b,0xb33bb3ea,0xb26d31ed,0xb33b32dd,0xb3c33388,0xb3fe33ea,0xb3c331ed,0xb1ed33c3,0x28b22d64,0x333bb0c4,
  0xb3ea31ed,0x2d64301d,0x32ddb388,0xb15fa8b2,0xb2dd31ed,0x33feabc6,0xb26dad64,0x2d64326d,0xb0c431ed,0x2ed7b2dd,0xabc63388,0x2248b3ea,
  0xabc631ed,0xb15fb3c3,0x33ea2d64,0xaed730c4,0x28b231ed,0xb388b01d,0xb01db388,0x31ed28b2,0x301d31ed,0xa2482bc6,0xb0c4ad64,0xb388b26d,
  0xb3ea33fe,0xb38833c3,0xb2dd333b,0xb1ed326d,0x32ddb3fe,0x2248b01d,0xb26d2ed7,0xb38833ea,0xb0c433fe,0x333babc6,0x2bc6b33b,0xb3fe30c4,
  0x2bc6b3fe,0xb1ed32dd,0x33eaaed7,0xb33ba8b2,0x28b233fe,0xad64b3c3,0x301d333b,0xb15fb26d,0xb01db3fe,0x33fe301d,0xb0c42ed7,0xad64b3ea,
  0x326d33fe,0xaed72bc6,0xb3c3b33b,0x2248b0c4,0xb3c3b3fe,0xb15fb2dd,0xa8b2aed7,0x2ed728b2,0x29ed29ed,0x29ed29ed,0x29ed29ed,0x29ed29ed,
  0x2bc32a6d,0x2add2bea,0x23c628c4,0xa81da0b2,0x2bc32add,0xa3c6281d,0xabc3aadd,0x23c6a81d,0x29ed2b3b,0xabfea564,0x295fa6d7,0x1a482b88,
  0x25642b88,0xa564ab88,0x25642b88,0xa564ab88,0xa0b22bc3,0x2a6daadd,0xabea23c6,0x28c4281d,0xa8c42bea,0x2a6da0b2,0x28c4abea,0xaa6d20b2,
  0xab3b2bfe,0xa564295f,0x26d79a48,0x2b88a9ed,0x29ed29ed,0x29ed29ed,0x29ed29ed,0x29ed29ed,0xabc3aa6d,0xaaddabea,0xa3c6a8c4,0x281d20b2,
  0x2bc32add,0xa3c6281d,0xabc3aadd,0x23c6a81d,0xa9edab3b,0x2bfe2564,0xa95f26d7,0x9a48ab88,0x25642b88,0xa564ab88,0x25642b88,0xa564ab88,
  0x20b2abc3,0xaa6d2add,0x2beaa3c6,0xa8c4a81d,0xa8c42bea,0x2a6da0b2,0x28c4abea,0xaa6d20b2,0x2b3babfe,0x2564a95f,0xa6d71a48,0xab8829ed,
  0x295f295f,0x295f295f,0x295f295f,0x295f295f,0x23c628c4,0xa81da0b2,0xabc3aa6d,0xaaddabea,0xa3c6281d,0xabc3aadd,0x23c6a81d,0x2bc32add,
  0xa95f26d7,0x9a48ab88,0x29ed2b3b,0xabfea564,0xab882564,0x2b88a564,0xab882564,0x2b88a564,0xabea23c6,0x28c4281d,0x20b2abc3,0xaa6d2add,
  0xaa6d20b2,0xa8c42bea,0x2a6da0b2,0x28c4abea,0xa6d71a48,0xab8829ed,0xab3b2bfe,0xa564295f,0x295f295f,0x295f295f,0x295f295f,0x295f295f,
  0xa3c6a8c4,0x281d20b2,0x2bc32a6d,0x2add2bea,0xa3c6281d,0xabc3aadd,0x23c6a81d,0x2bc32add,0x295fa6d7,0x1a482b88,0xa9edab3b,0x2bfe2564,
  0xab882564,0x2b88a564,0xab882564,0x2b88a564,0x2beaa3c6,0xa8c4a81d,0xa0b22bc3,0x2a6daadd,0xaa6d20b2,0xa8c42bea,0x2a6da0b2,0x28c4abea,
  0x26d79a48,0x2b88a9ed,0x2b3babfe,0x2564a95f,0xabfe2bfe,0xabfe2bfe,0xabfe2bfe,0xabfe2bfe,0xaadd2bea,0xa3c628c4,0x281da0b2,0x2bc3aa6d,
  0xa81d2bc3,0x2adda3c6,0x281dabc3,0xaadd23c6,0x9a482b88,0x29edab3b,0xabfe2564,0x295f26d7,0x26d72b3b,0xa6d7ab3b,0x26d72b3b,0xa6d7ab3b,
  0x2a6d2add,0xabeaa3c6,0x28c4a81d,0x20b22bc3,0x2bea2a6d,0xa0b228c4,0xabeaaa6d,0x20b2a8c4,0x2b8829ed,0x2b3b2bfe,0x2564295f,0xa6d79a48,
  0xabfe2bfe,0xabfe2bfe,0xabfe2bfe,0xabfe2bfe,0x2addabea,0x23c6a8c4,0xa81d20b2,0xabc32a6d,0xa81d2bc3,0x2adda3c6,0x281dabc3,0xaadd23c6,
  0x1a48ab88,0xa9ed2b3b,0x2bfea564,0xa95fa6d7,0x26d72b3b,0xa6d7ab3b,0x26d72b3b,0xa6d7ab3b,0xaa6daadd,0x2bea23c6,0xa8c4281d,0xa0b2abc3,
  0x2bea2a6d,0xa0b228c4,0xabeaaa6d,0x20b2a8c4,0xab88a9ed,0xab3babfe,0xa564a95f,0x26d71a48,0x1a489a48,0x1a489a48,0x1a489a48,0x1a489a48,
  0x281da0b2,0x2bc3aa6d,0x2addabea,0x23c6a8c4,0x2adda3c6,0x281dabc3,0xaadd23c6,0xa81d2bc3,0x2bfea564,0xa95fa6d7,0x9a482b88,0x29edab3b,
  0x2b3ba6d7,0xab3b26d7,0x2b3ba6d7,0xab3b26d7,0x28c4a81d,0x20b22bc3,0xaa6daadd,0x2bea23c6,0x20b2a8c4,0x2bea2a6d,0xa0b228c4,0xabeaaa6d,
  0xa564a95f,0x26d71a48,0x2b8829ed,0x2b3b2bfe,0x1a489a48,0x1a489a48,0x1a489a48,0x1a489a48,0xa81d20b2,0xabc32a6d,0xaadd2bea,0xa3c628c4,
  0x2adda3c6,0x281dabc3,0xaadd23c6,0xa81d2bc3,0xabfe2564,0x295f26d7,0x1a48ab88,0xa9ed2b3b,0x2b3ba6d7,0xab3b26d7,0x2b3ba6d7,0xab3b26d7,
  0xa8c4281d,0xa0b2abc3,0x2a6d2add,0xabeaa3c6,0x20b2a8c4,0x2bea2a6d,0xa0b228c4,0xabeaaa6d,0x2564295f,0xa6d79a48,0xab88a9ed,0xab3babfe,
  0xa95fa95f,0xa95fa95f,0xa95fa95f,0xa95fa95f,0xa3c6a8c4,0x281d20b2,0x2bc32a6d,0x2add2bea,0x23c6a81d,0x2bc32add,0xa3c6281d,0xabc3aadd,
  0x295fa6d7,0x1a482b88,0xa9edab3b,0x2bfe2564,0x2b88a564,0xab882564,0x2b88a564,0xab882564,0x2beaa3c6,0xa8c4a81d,0xa0b22bc3,0x2a6daadd,
  0x2a6da0b2,0x28c4abea,0xaa6d20b2,0xa8c42bea,0x26d79a48,0x2b88a9ed,0x2b3babfe,0x2564a95f,0xa95fa95f,0xa95fa95f,0xa95fa95f,0xa95fa95f,
  0x23c628c4,0xa81da0b2,0xabc3aa6d,0xaaddabea,0x23c6a81d,0x2bc32add,0xa3c6281d,0xabc3aadd,0xa95f26d7,0x9a48ab88,0x29ed2b3b,0xabfea564,
  0x2b88a564,0xab882564,0x2b88a564,0xab882564,0xabea23c6,0x28c4281d,0x20b2abc3,0xaa6d2add,0x2a6da0b2,0x28c4abea,0xaa6d20b2,0xa8c42bea,
  0xa6d71a48,0xab8829ed,0xab3b2bfe,0xa564295f,0x29ed29ed,0x29ed29ed,0x29ed29ed,0x29ed29ed,0x2bc32a6d,0x2add2bea,0x23c628c4,0xa81da0b2,
  0x2bc32add,0xa3c6281d,0xabc3aadd,0x23c6a81d,0x29ed2b3b,0xabfea564,0x295fa6d7,0x1a482b88,0x25642b88,0xa564ab88,0x25642b88,0xa564ab88,
  0xa0b22bc3,0x2a6daadd,0xabea23c6,0x28c4281d,0xa8c42bea,0x2a6da0b2,0x28c4abea,0xaa6d20b2,0xab3b2bfe,0xa564295f,0x26d79a48,0x2b88a9ed,
  0x29ed29ed,0x29ed29ed,0x29ed29ed,0x29ed29ed,0xabc3aa6d,0xaaddabea,0xa3c6a8c4,0x281d20b2,0x2bc32add,0xa3c6281d,0xabc3aadd,0x23c6a81d,
  0xa9edab3b,0x2bfe2564,0xa95f26d7,0x9a48ab88,0x25642b88,0xa564ab88,0x25642b88,0xa564ab88,0x20b2abc3,0xaa6d2add,0x2beaa3c6,0xa8c4a81d,
  0xa8c42bea,0x2a6da0b2,0x28c4abea,0xaa6d20b2,0x2b3babfe,0x2564a95f,0xa6d71a48,0xab8829ed,0x9a481a48,0x9a481a48,0x9a481a48,0x9a481a48,
  0xa81d20b2,0xabc32a6d,0xaadd2bea,0xa3c628c4,0xaadd23c6,0xa81d2bc3,0x2adda3c6,0x281dabc3,0xabfe2564,0x295f26d7,0x1a48ab88,0xa9ed2b3b,
  0xab3b26d7,0x2b3ba6d7,0xab3b26d7,0x2b3ba6d7,0xa8c4281d,0xa0b2abc3,0x2a6d2add,0xabeaa3c6,0xa0b228c4,0xabeaaa6d,0x20b2a8c4,0x2bea2a6d,
  0x2564295f,0xa6d79a48,0xab88a9ed,0xab3babfe,0x9a481a48,0x9a481a48,0x9a481a48,0x9a481a48,0x281da0b2,0x2bc3aa6d,0x2addabea,0x23c6a8c4,
  0xaadd23c6,0xa81d2bc3,0x2adda3c6,0x281dabc3,0x2bfea564,0xa95fa6d7,0x9a482b88,0x29edab3b,0xab3b26d7,0x2b3ba6d7,0xab3b26d7,0x2b3ba6d7,
  0x28c4a81d,0x20b22bc3,0xaa6daadd,0x2bea23c6,0xa0b228c4,0xabeaaa6d,0x20b2a8c4,0x2bea2a6d,0xa564a95f,0x26d71a48,0x2b8829ed,0x2b3b2bfe,
  0xabfe2bfe,0xabfe2bfe,0xabfe2bfe,0xabfe2bfe,0xaadd2bea,0xa3c628c4,0x281da0b2,0x2bc3aa6d,0xa81d2bc3,0x2adda3c6,0x281dabc3,0xaadd23c6,
  0x9a482b88,0x29edab3b,0xabfe2564,0x295f26d7,0x26d72b3b,0xa6d7ab3b,0x26d72b3b,0xa6d7ab3b,0x2a6d2add,0xabeaa3c6,0x28c4a81d,0x20b22bc3,
  0x2bea2a6d,0xa0b228c4,0xabeaaa6d,0x20b2a8c4,0x2b8829ed,0x2b3b2bfe,0x2564295f,0xa6d79a48,0xabfe2bfe,0xabfe2bfe,0xabfe2bfe,0xabfe2bfe,
  0x2addabea,0x23c6a8c4,0xa81d20b2,0xabc32a6d,0xa81d2bc3,0x2adda3c6,0x281dabc3,0xaadd23c6,0x1a48ab88,0xa9ed2b3b,0x2bfea564,0xa95fa6d7,
  0x26d72b3b,0xa6d7ab3b,0x26d72b3b,0xa6d7ab3b,0xaa6daadd,0x2bea23c6,0xa8c4281d,0xa0b2abc3,0x2bea2a6d,0xa0b228c4,0xabeaaa6d,0x20b2a8c4,
  0xab88a9ed,0xab3babfe,0xa564a95f,0x26d71a48,0x3bfb3bff,0x3be53bf2,0x3bbf3bd4,0x3b873ba5,0x3bd03bfb,0x3b013b7c,0x399d3a60,0x378538bc,
  0x35173b52,0xbbc9b7c8,0xb074ba9b,0x3bfe391b,0x319e3b27,0xbbf3b979,0x363cb80a,0x3a2d3bc5,0xba093986,0x3a7eb8f8,0xbae5385f,0x3b3db77a,
  0xbabd393c,0x3bb0b699,0xbc00305b,0x3ba730d7,0xbb2a35c8,0xb8353bb2,0x3a64b1e8,0x3962bbf7,0xba90350b,0xba413bff,0x3602340e,0x3bf6bad8,
  0xac6aa5e4,0xb122af59,0xb402b294,0xb56ab4b7,0xb2deac9c,0xb7bdb5a5,0xb9b3b8d6,0xbb10ba73,0xbb96b676,0xb359bafe,0x3bec3884,0x2a163a29,
  0xbbe0b72c,0x2f27b9d6,0x3b5e3ae8,0xb91633a2,0xb941b9c9,0x38ad3a45,0xb80fbab3,0x36d23b13,0xb850ba0d,0x346f3b4a,0x1fdbbbed,0xb4ab3be8,
  0x3721bb76,0xbace3463,0xb8d13bdd,0x39ebadfb,0x3894bb98,0xb8fd281f,0xbb6a3bbd,0x2e2d3825,0x3b3f3b65,0x3ae83b16,0x3a813ab6,0x3a0d3a49,
  0x3263356a,0xad972b43,0xb5dfb359,0xb8eeb7f3,0xa9b139aa,0xbbedba25,0x3340b889,0x3b983afb,0xbaa2aa16,0xb4cfbb8e,0x3c0038ad,0xb44b38e5,
  0xbb853625,0x3bbdb4c3,0xbbe432ad,0x3bfbaf8b,0xbaacb6d2,0x39243954,0xb65fbace,0x2fbd3bb8,0xb9661648,0xba603bf8,0x383a31cf,0x3b27bbb3,
  0x3219b9eb,0xbb1836f4,0xb9903be5,0x37dd3010,0xb6c6b61a,0xb80ab76f,0xb8a8b85a,0xb93cb8f3,0xbbd7bb87,0xbbf8bbfd,0xbb71bbc9,0xba4dbaf1,
  0xbbfeb9a6,0x305bb91f,0x3bcb3a97,0xb50b37d2,0xb87abbfe,0x3ba13546,0x24523a7e,0xbbb5ba54,0xb576bb63,0x340e3ba3,0xb13bbbd3,0x2c9c3bf2,
  0x386abb3d,0xba2139f8,0x3b57b835,0xbbf13432,0x39e7bc00,0xb8d6adc9,0xbacb3bde,0x372c3457,0x3bdab962,0x3764bb35,0xb9c03122,0xbaf73bef,
  0x398b39cd,0x38fd3946,0x386538b2,0x37853815,0xba85b9c9,0xbb92bb1e,0xbbfebbdd,0xbbc2bbf5,0xb66b3682,0xbb01bb94,0x387fb371,0x3a2d3beb,
  0xbac7bb76,0x3a00ad33,0x36bb3bd4,0xbbeab79b,0xbc0026ad,0x3bf32c38,0xbbd6b109,0x3ba733eb,0x3153bbff,0xb70a3b9e,0x396bba9b,0xbade390c,
  0xb5d4b5bc,0xbbb03b2c,0x32013830,0x3bf6ba67,0x3bccbb52,0x2c06b92e,0xbb83385f,0xb8c73bab,0xb9c5b982,0xba41ba04,0xbab0ba7a,0xbb10bae1,
  0xb8a3b986,0xb52fb74e,0xa94db1e8,0x33d32e91,0xbb54bb4f,0x37bdb523,0x3a9e3bc8,0xb916308d,0x3840b5c8,0x394a3bf9,0xbb42b294,0xb0a6bb0a,
  0x251bbbff,0xaf273bfc,0x327cbbe6,0xb4ab3bc0,0x3be325e4,0xbb2fb4e7,0x39e33884,0xb81aba35,0x3b73bb78,0xb46fb715,0xbbdc3ad1,0x2e2d38cc,
  0x33283676,0x3bfcba19,0x3581bab3,0xba6b3493,0x363136dd,0x34cf3581,0x32c6341a,0x2fbd3153,0xbae1bb65,0xb970ba39,0xb715b889,0xb16cb4f3,
  0xb9a12a7a,0xb924bbfe,0x3a933042,0x37dd3bcc,0x308db9aa,0x3b453b07,0xb94632ad,0xb845bbfa,0xbb68b55e,0x3b1836bb,0xbabab805,0x3a4d38a3,
  0x3bc0b625,0xbbfe2ec3,0x3b9431cf,0xba89b742,0x9cb6b95d,0xbbf8396b,0xb1b63a5c,0x3bb5b840,0x38cc9648,0x3b81bbac,0xac38b85a,0xbbce3933,
  0xbb60bb3a,0xbba1bb83,0xbbd2bbbc,0xbbf1bbe3,0x3815361a,0x39df3907,0x3b2c3a97,0x3be23b9c,0xb9afbbfd,0x3a21294d,0x388e3bee,0xbaf7b328,
  0x3beb39a6,0xb6af37a6,0xba04bbd3,0x3ac42d00,0x360ebb89,0xb7643b42,0x3855baeb,0xb8ee3a85,0x33eb3b63,0x28e8bbf5,0xb5233bde,0x389ebb21,
  0x3c00b9f0,0x2d97b9e3,0xbbdf38db,0xb44b3ac7,0xba673c00,0x358d3487,0x3bfcbab6,0x330fba15,0x3b7a3bf1,0x394a3a93,0x33893764,0xb3d39cb6,
  0x3afb3be2,0x35eb3946,0xb4c328e8,0xbaa9b8cc,0x27763af7,0xbb2fbaba,0x3a76ad97,0x30a63b60,0xaf8b3ac4,0xb994bb94,0x3bf8358d,0xb8743815,
  0xbb4c38ee,0x3bfcb1b6,0xbad5b4cf,0x381a39af,0xbbb3389e,0x3b592c38,0xb76fb970,0xb24b3beb,0xb9d2344b,0xbb923bd2,0xb0f03924,0x3a6bb60e,
  0xb8f3330f,0xbc003b2c,0xb91f3b45,0x323233eb,0xb5b1afbd,0xba00b88e,0xbbc6bb18,0xbbc2bc00,0xb7d2b16c,0xbb6fba04,0xbba3bbfe,0xb86fba67,
  0xbbffb7dd,0x370ab855,0x38b73bf8,0xbbeab631,0xbbf2b845,0x39bcb523,0x2dc93b81,0xbaa5bae1,0xb68dba4d,0xac063bdf,0x382abba1,0xbade39a1,
  0xb457ba89,0xb6543bfc,0x3b16b9df,0xbbd8308d,0x397dbbb5,0xb52fb2c6,0xbbe73a21,0xb8c73b68,0x3a49bbce,0x2311b715,0xba2536af,0xbbd93bc0,
  0xb958b785,0xbb81ba9e,0xbbefbbf3,0xba89bb73,0xbbf7bbc2,0xb9b8bb42,0xaf59b70a,0x384a3328,0xbb8bba2d,0x39dfb27c,0x34263bb0,0xbbceb98b,
  0xb4b7bbea,0x3b6c39e3,0xbafe2c06,0x3185ba85,0xaadebba7,0xb6af3bdc,0x3a58ba41,0xbbe2366b,0x3a29bade,0xbc003581,0x3a45352f,0xb2f7bac7,
  0x3b37bbf6,0x28e8b865,0xbaee37bd,0xbac43c00,0x3b13b8c7,0x3b5cbbfe,0x3463b94a,0xb8993153,0xb9f4bb10,0xb58db87f,0x3029af27,0x389e35d4,
  0x2dfbb3d3,0x399936bb,0x3bf23b2f,0x3ac13bcc,0x3552b916,0x39703bd6,0xbbbab46f,0x330fb9c5,0x3ba530a6,0xb5f7396b,0xb7c8bbfc,0x3be138a3,
  0x3bfdb4ab,0xbb45b201,0x38e038fd,0xb16cbb54,0x391b381a,0xa17fbb83,0xb8f83b92,0x3bcfb840,0x36e82e2d,0x3bfebab0,0x37febb01,0xb845251b,
  0xb77a3a6b,0x3648294d,0x3bb2ba00,0x3a8cbbe3,0xb742b93c,0x2311b340,0x37a6340e,0x3aa93966,0x3b963a4d,0x3b7f3c00,0x380f3a21,0xb0be3219,
  0x3933b50b,0x35eb3be4,0xbbf5b8d6,0x3874b6c6,0x39413bb5,0xbbffb65f,0x38d1b764,0x33ba3bd7,0x3b9c2c9c,0xb994b83a,0x34873ae8,0x324bbbfe,
  0xb7213bf1,0x3b47b990,0xbbbf2d97,0x38c1387a,0x2d00372c,0x3b59b8a8,0x3a39bbed,0xb232b576,0xbbfb3af7,0xb9743b71,0x307434cf,0x3adbb86a,
  0x3b213a0d,0x3c003bcb,0x3b073bbd,0x386f39e7,0x351738ee,0xb599a452,0xbae5b924,0xbbe9bbda,0x3a153b98,0xbb6fb13b,0x2ec3ba60,0x3aa53b3f,
  0xba09344b,0xa884bb57,0x3a643b18,0xbbc3b263,0xb4f33bfb,0x39bcbacb,0xbbac380a,0x3bd8a9b1,0xbb2aafbd,0x36a439c0,0x3402bbf8,0xba6f3aa2,
  0xbbfa3b27,0xb6543a81,0x3907b05b,0x3bd9bb85,0x2c6ab7dd,0xb9da35df,0xbbec3ba1,0xb8203aac,0x3bf53b87,0x3b6c3bec,0x392e3a7e,0x32f73721,
  0xb9e7b785,0xbbfcbb5e,0xba81bbb0,0xb43eb894,0x379b3bfe,0xbc00b80f,0x374eb835,0x38993bfb,0xbb3fba2d,0x3b329fdb,0xb3403a41,0xb8eabbd0,
  0xb90c3b3d,0x3b5cb8d1,0xbbf93122,0x3ac13517,0x29b1bba7,0xb94f3b6a,0x3be4b7bd,0xbaf4b19e,0xbbab3962,0xb9993bbf,0x34e73359,0x3be1ba09,
  0x3b85bbf6,0x353ab99d,0xb83a2f27,0xbbf03abd,0x2e91356a,0xb5f7b074,0xba19b8ad,0xbbcfbb2a,0xb966bb10,0xaba7b63c,0x38a8346f,0x3bb73a90,
  0xbb0aaa16,0xa17fbae5,0x3b1e3ace,0xba8c2c6a,0x36c6b916,0x36ff3c00,0xbbcbb8fd,0x3a50b2de,0xba35b6d2,0x36483a64,0x2d33bbe5,0xb84a3b96,
  0x3bfeb4ab,0xb9fcb602,0x313b3b01,0x37e8bbe0,0x3493b9eb,0xb9b83402,0xbb9e3bc9,0xb1853941,0x35762e2d,0x3b90b9b3,0x3acbbbf3,0x2fefb850,
  0x3a543bcf,0x2884374e,0xb9f8b648,0xbbe9bbab,0x398b3bb7,0xb4db3340,0xbbdcb9fc,0xb911bb85,0xb4323a8c,0xb6a4bbf9,0x3b3539b8,0xbbc3ae91,
  0xb66b3a50,0xad65bbe4,0x38653b90,0xbb0db966,0xbbef384a,0x39da34e7,0x2b43bb6c,0xba6f3b0a,0xbc0037e8,0x3759383a,0x387fbbfc,0xbbf636c6,
  0xb7f33185,0xbb7f3a19,0xbb8e3c00,0xb8203a35,0xb5d42fef,0xba1d38a8,0xbbd63b32,0xbba93bfe,0xb8e5b2f7,0xbbffbb1e,0xb954bb5c,0x30beb493,
  0xb9c5b43e,0xbb9fbbcb,0xb201b94f,0x3a313576,0xbbb8b899,0x3b47ad33,0xb6f43999,0xb3babbf5,0xbb54b8ea,0x3bf9313b,0xbab0353a,0x3790b9e7,
  0xb010bac1,0xb9743b9e,0x3bfdb5f7,0xb8c1b79b,0x251bbaf4,0xbb1b3acb,0x3a9e2ba7,0x2e5fbb3f,0x3af1bbe1,0x3599b92e,0xb546a17f,0xbadb390c,
  0x3b73bbf0,0x3929ba81,0x327cb6ff,0xb49f29b1,0xb825baa9,0x353aaec3,0x3b7c3994,0x3af43bfa,0x360eb0be,0x3bf43a64,0x388e3b47,0xb7372c6a,
  0x38bcb874,0x2ba73bac,0xb979bb59,0x3bf03742,0x3c0033ba,0xbb043402,0x3855b974,0xacce3b96,0x3bc5b24b,0xb6ffb907,0xb6993c00,0x3bb7b933,
  0x363138c1,0x3902bbec,0xbbdf3599,0x34ff3941,0x30d73232,0x39fcb7a6,0x3bffbb6f,0x3a50bb9c,0xb9a13adb,0xb47b380f,0x32c62884,0x3937b721,
  0x3ad8386f,0x3b903bf5,0x35a539bc,0xb7e8ad00,0x3b683be9,0x2ef538d1,0xba93b6a4,0xbb24bbfb,0x3a733aa5,0xbbfcb487,0x39d6b654,0xafef3b21,
  0x1cb63bc3,0xb7b2bbbf,0x3aba39da,0xbbfab517,0xb3a23bd8,0x3b32ba39,0xbb4a2311,0x343e3a15,0xbb603a6f,0x3a3d3074,0x31b6bb7f,0xbb9a3a09,
  0xbbe83bd9,0xb94f3b07,0xa81f35eb,0x38eab4f3,0xb9af3820,0xbbae3ae5,0xbbd23bff,0xba113b2a,0x319e389e,0xb929b426,0xbc00bb45,0xb911bb37,
  0xbbffbac1,0xb805bafe,0x382a217f,0x3bfd3b13,0xbabd330f,0x34dbba58,0x36023bfe,0xbb0db9f4,0xb68dbbe1,0x3a5c3a45,0xbbe7b648,0x3b89adfb,
  0xba90b16c,0x2d653aee,0x39b3bb81,0xbbf63552,0x397dbbcf,0xbbbc3463,0x338939b8,0x39f0bba5,0x32deb845,0xb7593029,0xbb5e39df,0xbba93bfd,
  0x3b7aba8c,0x3beebbf2,0x3a76bb6c,0x36ddb91b,0xbbe0ba89,0xba1dbbba,0x1fdbb6af,0x3a3136e8,0xa776b84a,0x3aeb37c8,0x3ad53c00,0xaa7a377a,
  0xb850bbce,0x3b9f38e0,0xbb6a28e8,0x3790b958,0x3b4cb185,0xb8db38f8,0x30f0bb5c,0x355e3bf7,0x3894bbe2,0xbbf937fe,0x399d358d,0x2e5fbb8b,
  0x39d232f7,0x341abbb2,0xbbc63999,0x395d34b7,0x3bd0bac4,0x3b1bbbef,0x363cb970,0xb49faade,0xb5b13899,0x30422f59,0x38b7b5f7,0x3b3aba29,
  0x3219b3d3,0x3b0438b7,0x3b713bfc,0x34ff397d,0x36e83aa9,0xb8b2adc9,0xbbefbb59,0xb5bcba49,0x3bd730a6,0xb902382a,0xa452bb92,0x39373b7a,
  0xb9583874,0x3371bb16,0x34263c00,0xb982bafb,0x387a381a,0x347bbbe7,0xbb573a00,0x3b242776,0xbb8b324b,0x31093a25,0x3a58bb6f,0xbb4f2f8b,
  0xb86a3a6b,0x2ef53389,0x39c0b70a,0x3bfabb4c,0xaadeb232,0xb83034c3,0xbaee39bc,0xbbff3bb3,0x3bda3bc2,0x37b23a76,0xb5df2c06,0xbb9ab9d2,
  0xbb37b86f,0xba7abbf8,0x3029b654,0x3b7838f3,0x32633bea,0xba3dbad5,0x3c00352f,0xba1135b1,0xb9f4baa5,0x3bc8376f,0xbbba2311,0x39cdb7d2,
  0xbaa23ade,0x3baeb0f0,0xb65fb94a,0xb7373bff,0x3552bbd8,0xbbe6391f,0x38e035eb,0x3682bbf2,0xbaac38c7,0xbbf43bc6,0xb9903b2f,0xacce368d,
  0x3bfdbbd9,0x3ad1bba3,0x37feb994,0x26adb457,0x38a33b9a,0xb8dba452,0xbb83bbae,0x2a7ab86a,0x37423b78,0xbab6b426,0xb907bbe6,0x39aa2ade,
  0xb8403a11,0x341abb57,0x294d3bf4,0xb55ebbda,0xb93339cd,0x3889ba58,0xb7a63ad1,0x3625bb37,0xbbe33737,0x304239c0,0x3b42bb04,0xb95db263,
  0xbb9c3682,0xb2ad3aee,0x3bf5b8b2,0x1648b9f4,0xb3282cce,0xb80535df,0xb9e33902,0xbb3a3aa2,0xad0026ad,0xb1cf3029,0xb4873371,0xb61a3552,
  0xba85b4ff,0xba5cbc00,0x3581b47b,0x3bfd3aac,0xbb21b5bc,0xb85abbba,0x3a393109,0x39a63bfd,0xbac7b937,0x3bbc365f,0xbbfeaef5,0x3b89b219,
  0xba15b982,0x3a9738e0,0xbb07b830,0x3b6336e8,0x3153bb24,0xbbee3990,0x36bb37b2,0x39f0bbd7,0x34f3bb4f,0xbbd337fe,0xaec33a7a,0x3c00b958,
  0x3bccbbfa,0x3aebbb71,0x396bba3d,0x36ddb87a,0x3bfabbff,0x3bdebbef,0x3bacbbc8,0x3b65bb8b,0x3bc03911,0x38303b6a,0xb946ad65,0xbb4fbbd0,
  0x3a353bfd,0xb85f30f0,0xbb1ebbbc,0x35c8b5b1,0x38cc3b0d,0xba7ab99d,0x3b943759,0xbbffb19e,0xb4933b89,0x31e8bbc6,0xad333bee,0xa5e4bbff,
  0xb8153bf6,0x3bc8b63c,0xac38ba1d,0xbb783abd,0xbbf539f0,0x329438b7,0x3b9ebaeb,0xb676b68d,0xbbeb3ba9,0xbbe63c00,0xbb2c3b9f,0xb9cd3a90,
  0xb79b36dd,0xb884382a,0xb92e38db,0xb9c9397d,0x33eb3a31,0xbad1b602,0xba04bbf9,0x3682b2de,0xb90c2a7a,0xbab3bbe7,0x374eb41a,0x3b763b7a,
  0xba673790,0x38b2b9b3,0xb5233b1b,0x26adbbe0,0xbbabb55e,0x3bdd3389,0xbbf9b042,0x3bff2776,0xbae12e5f,0xb3713b5e,0x3bfcb929,0xb5bcb850,
  0xae91b95d,0xbbd43a76,0x34e73805,0x3b52bb4c,0x308db49f,0xb1091fdb,0xb71534db,0xb9823894,0x3b0abb3a,0x3a9bbad5,0x3a19ba5c,0x3986b9d2,
  0x2f8bb7e8,0x3bde3979,0x376f3b32,0xb9aab0d7,0x3bb83b24,0xb1223855,0xbbfdba3d,0xaa16b9a1,0x3bb3afef,0xbab63699,0x391fb94f,0xb6253ad8,
  0x30103bfa,0xb359bbdf,0x35463bae,0xb6d2bb68,0x38f3343e,0x3889bbff,0xbba3353a,0x96483a73,0xbaf13b9a,0x38ad32c6,0x39f8bbf4,0xb9eb9cb6,
  0xb7d238ea,0xb2ad35a5,0x2dc92ba7,0x361ab3a2,0xba543a11,0xbace3a93,0xbb353b04,0xbb873b60,0x3bf23af4,0x31cf39d6,0xbb16b6ff,0xb9a6bbe8,
  0xb4323737,0xbbe5baba,0x2b43b902,0x3bfe39af,0x34573bf0,0xb85abb4a,0x3a2539fc,0xbb63b825,0xbbef2cce,0x3bc9b1b6,0xbb8e347b,0x3b3db60e,
  0xba493bb7,0x3a97a81f,0x34c3bb90,0xbc0038bc,0xb7f3b4ff,0xba7e3bd2,0x39542ef5,0x3962bc00,0xbafb3a50,0xbbd33b7c,0xbbf83bfc,0xbb653bc5,
  0x38e5b937,0x3835b88e,0x36f4b7b2,0x356ab631,0xbb13bbe9,0x31e8b6f4,0x3bf239da,0x36763af1,0x3be83911,0x340e3ab0,0xbb7cb759,0xb72cbb73,
  0x2dfbbbc3,0x32943bfd,0xb7c8bb7f,0x39c93a54,0x38253b0d,0xb8d6ba9e,0x39793a1d,0xba0db98b,0x3ba5ba6f,0xb884b546,0xb8f83bff,0x3b76b432,
  0xb8bc3bf6,0x3ae8b27c,0x3699bb9f,0xbb98366b,0x391bb820,0x3ab3b9f8,0x3bb2bb47,0x3bffbbef,0xbbc53ba9,0xbbed3bdc,0xbbff3bf9,0xbbfb3c00,
  0x377ab0be,0x3bdd3b35,0x2f593974,0xbb52b7f3,0x30d73a31,0xbbbdb865,0xb5a5bb1b,0x3b2735d4,0x3bf733ba,0xbbd42b43,0x3afeb599,0xb98638e5,
  0xbad83790,0x3a60b87f,0xb9d63929,0x393cb9c5,0x34b738c1,0x3a9bbb8e,0xba45a884,0xb5c83bb8,0xba732e5f,0xb80a3bd6,0x3b4ab4db,0x350bbb54,
  0xba293adb,0xb85f3954,0xb46336a4,0x25e43010,0x33a2b49f,0x305bb201,0x281fad65,0xac9c251b,0x3f803f80,0x3f803f80,0x3f803f80,0x3f803f80,
  0x3f803f80,0x3f803f80,0x3f803f80,0x3f803f80,0x3f803f80,0x3f803f80,0x3f803f80,0x3f803f80,0x3f803f80,0x3f803f80,0x3f803f80,0x3f803f80,
  0x3f803f80,0x3f803f80,0x3f803f80,0x3f803f80,0x3f803f80,0x3f803f80,0x3f803f80,0x3f803f80,0x3f803f80,0x3f803f80,0x3f803f80,0x3f803f80,
  0x3f803f80,0x3f803f80,0x3f803f80,0x3f803f80,0x3f803f80,0x3f803f80,0x3f803f80,0x3f803f80,0x3f803f80,0x3f803f80,0x3f803f80,0x3f803f80,
  0x3f803f80,0x3f803f80,0x3f803f80,0x3f803f80,0x3f803f80,0x3f803f80,0x3f803f80,0x3f803f80,0x3f803f80,0x3f803f80,0x3f803f80,0x3f803f80,
  0x3f803f80,0x3f803f80,0x3f803f80,0x3f803f80,0x3f803f80,0x3f803f80,0x3f803f80,0x3f803f80,0x3f803f80,0x3f803f80,0x3f803f80,0x3f803f80,
  0x3f803f80,0x3f803f80,0x3f803f80,0x3f803f80,0x3f803f80,0x3f803f80,0x3f803f80,0x3f803f80,0x3f803f80,0x3f803f80,0x3f803f80,0x3f803f80,
  0x3f803f80,0x3f803f80,0x3f803f80,0x3f803f80,0x3f803f80,0x3f803f80,0x3f803f80,0x3f803f80,0x3f803f80,0x3f803f80,0x3f803f80,0x3f803f80,
  0x3f803f80,0x3f803f80,0x3f803f80,0x3f803f80,0x3f803f80,0x3f803f80,0x3f803f80,0x3f803f80,0x3f803f80,0x3f803f80,0x3f803f80,0x3f803f80,
  0x3f803f80,0x3f803f80,0x3f803f80,0x3f803f80,0x3f803f80,0x3f803f80,0x3f803f80,0x3f803f80,0x3f803f80,0x3f803f80,0x3f803f80,0x3f803f80,
  0x3f803f80,0x3f803f80,0x3f803f80,0x3f803f80,0x3f803f80,0x3f803f80,0x3f803f80,0x3f803f80,0x3f803f80,0x3f803f80,0x3f803f80,0x3f803f80,
  0x3f803f80,0x3f803f80,0x3f803f80,0x3f803f80,0x3f803f80,0x3f803f80,0x3f803f80,0x3f803f80,0x3f803f80,0x3f803f80,0x3f803f80,0x3f803f80,
  0x3f803f80,0x3f803f80,0x3f803f80,0x3f803f80,0x3f803f80,0x3f803f80,0x3f803f80,0x3f803f80,0x3f803f80,0x3f803f80,0x3f803f80,0x3f803f80,
  0x3f803f80,0x3f803f80,0x3f803f80,0x3f803f80,0x3f803f80,0x3f803f80,0x3f803f80,0x3f803f80,0x3f803f80,0x3f803f80,0x3f803f80,0x3f803f80,
  0x3f803f80,0x3f803f80,0x3f803f80,0x3f803f80,0x3f803f80,0x3f803f80,0x3f803f80,0x3f803f80,0x3f803f80,0x3f803f80,0x3f803f80,0x3f803f80,
  0x3f803f80,0x3f803f80,0x3f803f80,0x3f803f80,0x3f803f80,0x3f803f80,0x3f803f80,0x3f803f80,0x3f803f80,0x3f803f80,0x3f803f80,0x3f803f80,
  0x3f803f80,0x3f803f80,0x3f803f80,0x3f803f80,0x3f803f80,0x3f803f80,0x3f803f80,0x3f803f80,0x3f803f80,0x3f803f80,0x3f803f80,0x3f803f80,
  0x3f803f80,0x3f803f80,0x3f803f80,0x3f803f80,0x3f803f80,0x3f803f80,0x3f803f80,0x3f803f80,0x3f803f80,0x3f803f80,0x3f803f80,0x3f803f80,
  0x3f803f80,0x3f803f80,0x3f803f80,0x3f803f80,0x3f803f80,0x3f803f80,0x3f803f80,0x3f803f80,0x3f803f80,0x3f803f80,0x3f803f80,0x3f803f80,
  0x3f803f80,0x3f803f80,0x3f803f80,0x3f803f80,0x3f803f80,0x3f803f80,0x3f803f80,0x3f803f80,0x3f803f80,0x3f803f80,0x3f803f80,0x3f803f80,
  0x3f803f80,0x3f803f80,0x3f803f80,0x3f803f80,0x3f803f80,0x3f803f80,0x3f803f80,0x3f803f80,0x3f803f80,0x3f803f80,0x3f803f80,0x3f803f80,
  0x3f803f80,0x3f803f80,0x3f803f80,0x3f803f80,0x3f803f80,0x3f803f80,0x3f803f80,0x3f803f80,0x3f803f80,0x3f803f80,0x3f803f80,0x3f803f80,
  0x3f803f80,0x3f803f80,0x3f803f80,0x3f803f80,0x3f803f80,0x3f803f80,0x3f803f80,0x3f803f80,0x3f803f80,0x3f803f80,0x3f803f80,0x3f803f80,
  0x3f803f80,0x3f803f80,0x3f803f80,0x3f803f80,0x3f803f80,0x3f803f80,0x3f803f80,0x3f803f80,0x3f803f80,0x3f803f80,0x3f803f80,0x3f803f80,
  0x3f803f80,0x3f803f80,0x3f803f80,0x3f803f80,0x3f803f80,0x3f803f80,0x3f803f80,0x3f803f80,0x3f803f80,0x3f803f80,0x3f803f80,0x3f803f80,
  0x3f803f80,0x3f803f80,0x3f803f80,0x3f803f80,0x3f803f80,0x3f803f80,0x3f803f80,0x3f803f80,0x3f803f80,0x3f803f80,0x3f803f80,0x3f803f80,
  0x3f803f80,0x3f803f80,0x3f803f80,0x3f803f80,0x3f803f80,0x3f803f80,0x3f803f80,0x3f803f80,0x3f803f80,0x3f803f80,0x3f803f80,0x3f803f80,
  0x3f803f80,0x3f803f80,0x3f803f80,0x3f803f80,0x3f803f80,0x3f803f80,0x3f803f80,0x3f803f80,0x3f803f80,0x3f803f80,0x3f803f80,0x3f803f80,
  0x3f803f80,0x3f803f80,0x3f803f80,0x3f803f80,0x3f803f80,0x3f803f80,0x3f803f80,0x3f803f80,0x3f803f80,0x3f803f80,0x3f803f80,0x3f803f80,
  0x3f803f80,0x3f803f80,0x3f803f80,0x3f803f80,0x3f803f80,0x3f803f80,0x3f803f80,0x3f803f80,0x3f803f80,0x3f803f80,0x3f803f80,0x3f803f80,
  0x3f803f80,0x3f803f80,0x3f803f80,0x3f803f80,0x3f803f80,0x3f803f80,0x3f803f80,0x3f803f80,0x3f803f80,0x3f803f80,0x3f803f80,0x3f803f80,
  0x3f803f80,0x3f803f80,0x3f803f80,0x3f803f80,0x3f803f80,0x3f803f80,0x3f803f80,0x3f803f80,0x3f803f80,0x3f803f80,0x3f803f80,0x3f803f80,
  0x3f803f80,0x3f803f80,0x3f803f80,0x3f803f80,0x3f803f80,0x3f803f80,0x3f803f80,0x3f803f80,0x3f803f80,0x3f803f80,0x3f803f80,0x3f803f80,
  0x3f803f80,0x3f803f80,0x3f803f80,0x3f803f80,0x3f803f80,0x3f803f80,0x3f803f80,0x3f803f80,0x3f803f80,0x3f803f80,0x3f803f80,0x3f803f80,
  0x3f803f80,0x3f803f80,0x3f803f80,0x3f803f80,0x3f803f80,0x3f803f80,0x3f803f80,0x3f803f80,0x3f803f80,0x3f803f80,0x3f803f80,0x3f803f80,
  0x3f803f80,0x3f803f80,0x3f803f80,0x3f803f80,0x3f803f80,0x3f803f80,0x3f803f80,0x3f803f80,0x3f803f80,0x3f803f80,0x3f803f80,0x3f803f80,
  0x3f803f80,0x3f803f80,0x3f803f80,0x3f803f80,0x3f803f80,0x3f803f80,0x3f803f80,0x3f803f80,0x3f803f80,0x3f803f80,0x3f803f80,0x3f803f80,
  0x3f803f80,0x3f803f80,0x3f803f80,0x3f803f80,0x3f803f80,0x3f803f80,0x3f803f80,0x3f803f80,0x3f803f80,0x3f803f80,0x3f803f80,0x3f803f80,
  0x3f803f80,0x3f803f80,0x3f803f80,0x3f803f80,0x3f803f80,0x3f803f80,0x3f803f80,0x3f803f80,0x3f803f80,0x3f803f80,0x3f803f80,0x3f803f80,
  0x3f803f80,0x3f803f80,0x3f803f80,0x3f803f80,0x3f803f80,0x3f803f80,0x3f803f80,0x3f803f80,0x3f803f80,0x3f803f80,0x3f803f80,0x3f803f80,
  0x3f803f80,0x3f803f80,0x3f803f80,0x3f803f80,0x3f803f80,0x3f803f80,0x3f803f80,0x3f803f80,0x3f803f80,0x3f803f80,0x3f803f80,0x3f803f80,
  0x3f803f80,0x3f803f80,0x3f803f80,0x3f803f80,0x3f803f80,0x3f803f80,0x3f803f80,0x3f803f80,0x3f803f80,0x3f803f80,0x3f803f80,0x3f803f80,
  0x3f803f80,0x3f803f80,0x3f803f80,0x3f803f80,0x3f803f80,0x3f803f80,0x3f803f80,0x3f803f80,0x3f803f80,0x3f803f80,0x3f803f80,0x3f803f80,
  0x3f803f80,0x3f803f80,0x3f803f80,0x3f803f80,
};

__device__ __align__(128) float    g_part[16][8][2176];
__device__ __align__(128) float    g_kv[16][2176];
__device__ __align__(128) uint4    g_o[16 * 16 * 1024];
__device__ __align__(128) unsigned g_ocnt[2 * 16 * 32];
__device__ unsigned g_epoch[128];
#define GSTAMP(role, i) do {} while (0)
#define STAMP(role, i) do {} while (0)
#define PDUMP(role) do {} while (0)
#define PROF_SMEM 0

constexpr int STAGE_BYTES = 57344;
constexpr int OFF_H = 4 * 16384, OFF_VP = 9 * 16384, OFF_SPARE = 10 * 16384;
constexpr int OFF_XT = 172032, XT_STRIDE = 4112;
constexpr int OFF_BAR = 204928, OFF_EPOCH = OFF_BAR + 640, OFF_EX = OFF_BAR + 656, OFF_D = OFF_BAR + 672, OFF_SCALE = OFF_BAR + 704;
constexpr int OFF_F2F = 205824, OFF_F2I = 207872, OFF_F4 = 209920, OFF_ONES = 214016, OFF_KVB = 214016;
constexpr int OFF_STG = 219136, STG_STRIDE = 4352, SMEM_TOTAL = 232192 + PROF_SMEM;
enum { B_FULL1 = 0, B_EMPTY1 = 3, B_Q = 6, B_ODONE1 = 7, B_O1RDY = 8, B_XRAW = 10, B_XT = 11, B_KV = 12, B_Y = 13, B_PKFREE = 14, B_AFREE = 15,
       B_STG = 18, B_ODONE = 24, B_XFREE = 25, B_FULL2 = 33, B_CONS2 = 49, B_COUNT = 62 };
__host__ __device__ constexpr int bar_count(int i) {
  return i < B_EMPTY1 ? 1 : i < B_Q ? 4 : i == B_XT ? 4 : i == B_KV ? 2 : i == B_Y ? 9 : i == B_PKFREE ? 8
       : (i >= B_AFREE && i < B_STG) ? 16 : (i == B_ODONE || i == B_ODONE1) ? 8 : (i >= B_XFREE && i < B_FULL2) ? 4
       : (i >= B_CONS2 && i <= B_CONS2 + 10) ? 4 : i >= B_CONS2 ? 2 : (i >= B_FULL2 && i < B_FULL2 + 7) ? 2 : 1;
}
__host__ __device__ constexpr uint64_t bar_counts(int r) {
  uint64_t v = 0;
  for (int w = 0; w < 11; w++) v |= (uint64_t)(bar_count(1 + 11 * r + w) - 1) << (4 * w);
  return v;
}
constexpr uint64_t SLOT_A = 0x9245392453924594ull;
constexpr uint64_t SLOT_B = 0x7610876108761032ull;
constexpr int SPIN_LIMIT = 1 << 22;
#define PKV CU_TENSOR_MAP_L2_PROMOTION_L2_128B
#define BPRE B_KV
#define PFD 3
#define PD1 400
#define PD2 100
#define E1C 2
#define OSP 4
#define QPF 4
#define TSPLIT 1
#define OC0 2
#define OC1 2
#define BSPL 4
#define BPACE 400
#define NPOS 0
#define O1POS 1
#define HL1 4
#define OCH 3
#define O1D 3
#define QPOS 2
#define HSTART 1500
#define PACE 1050
#define OC 1

__device__ __forceinline__ uint32_t smem_u32(const void* p) { return (uint32_t)__cvta_generic_to_shared(p); }
__device__ __forceinline__ void wg_fence() { asm volatile("wgmma.fence.sync.aligned;" ::: "memory"); }
__device__ __forceinline__ void wg_commit() { asm volatile("wgmma.commit_group.sync.aligned;" ::: "memory"); }
template <int N> __device__ __forceinline__ void wg_wait() { asm volatile("wgmma.wait_group.sync.aligned %0;" ::"n"(N) : "memory"); }
template <int N> __device__ __forceinline__ void keep(float (&d)[N]) {
#pragma unroll
  for (int i = 0; i < N; i++) asm volatile("" : "+f"(d[i])::"memory");
}
__device__ __forceinline__ uint64_t mkdesc(uint32_t addr, uint32_t lbo, uint32_t sbo, uint32_t swz) {
  uint32_t lo = ((addr & 0x3FFFF) >> 4) | ((lbo >> 4) << 16), hi = (sbo >> 4) | (swz << 30);
  return ((uint64_t)hi << 32) | lo;
}
__device__ __forceinline__ void mbar_init(uint32_t bar, int cnt) { asm volatile("mbarrier.init.shared::cta.b64 [%0], %1;" ::"r"(bar), "r"(cnt)); }
__device__ __forceinline__ void mbar_expect(uint32_t bar, int bytes) { asm volatile("mbarrier.arrive.expect_tx.shared::cta.b64 _, [%0], %1;" ::"r"(bar), "r"(bytes) : "memory"); }
__device__ __forceinline__ void mbar_arrive(uint32_t bar) { asm volatile("mbarrier.arrive.shared::cta.b64 _, [%0];" ::"r"(bar) : "memory"); }
__device__ __forceinline__ void mbar_arrive_cl(uint32_t bar, uint32_t cta) {
  asm volatile("{\n.reg .b32 r;\nmapa.shared::cluster.u32 r, %0, %1;\nmbarrier.arrive.shared::cluster.b64 _, [r];\n}\n" ::"r"(bar), "r"(cta) : "memory");
}
__device__ __forceinline__ void mbar_wait(uint32_t bar, uint32_t parity) {
  asm volatile("{\n.reg .pred p;\n.reg .u32 n;\nmov.u32 n, 0;\n"
               "W_%=:\nmbarrier.try_wait.parity.shared::cta.b64 p, [%0], %1;\n@p bra D_%=;\n"
               "add.u32 n, n, 1;\nsetp.lt.u32 p, n, %2;\n@p bra W_%=;\ntrap;\nD_%=:\n}\n" ::"r"(bar), "r"(parity), "n"(SPIN_LIMIT) : "memory");
}
__device__ __forceinline__ void fence_async() { asm volatile("fence.proxy.async.shared::cta;" ::: "memory"); }
__device__ __forceinline__ void bar_sync(int id) { asm volatile("bar.sync %0, 128;" ::"r"(id) : "memory"); }
__device__ __forceinline__ void tma2d(uint32_t dst, const CUtensorMap* m, int c0, int c1, uint32_t bar) {
  asm volatile("cp.async.bulk.tensor.2d.shared::cluster.global.mbarrier::complete_tx::bytes [%0], [%1, {%3, %4}], [%2];"
               ::"r"(dst), "l"(m), "r"(bar), "r"(c0), "r"(c1) : "memory");
}
__device__ __forceinline__ void tma2d_mc(uint32_t dst, const CUtensorMap* m, int c0, int c1, uint32_t bar) {
  asm volatile("cp.async.bulk.tensor.2d.shared::cluster.global.mbarrier::complete_tx::bytes.multicast::cluster [%0], [%1, {%3, %4}], [%2], %5;"
               ::"r"(dst), "l"(m), "r"(bar), "r"(c0), "r"(c1), "h"((uint16_t)3) : "memory");
}
__device__ __forceinline__ void tma3d(uint32_t dst, const CUtensorMap* m, int c0, int c1, int c2, uint32_t bar) {
  asm volatile("cp.async.bulk.tensor.3d.shared::cluster.global.mbarrier::complete_tx::bytes [%0], [%1, {%3, %4, %5}], [%2];"
               ::"r"(dst), "l"(m), "r"(bar), "r"(c0), "r"(c1), "r"(c2) : "memory");
}
__device__ __forceinline__ void tma4d(uint32_t dst, const CUtensorMap* m, int c0, int c1, int c2, int c3, uint32_t bar) {
  asm volatile("cp.async.bulk.tensor.4d.shared::cluster.global.mbarrier::complete_tx::bytes [%0], [%1, {%3, %4, %5, %6}], [%2];"
               ::"r"(dst), "l"(m), "r"(bar), "r"(c0), "r"(c1), "r"(c2), "r"(c3) : "memory");
}
__device__ __forceinline__ void bulk_ld(uint32_t dst, const void* src, int bytes, uint32_t bar) {
  asm volatile("cp.async.bulk.shared::cluster.global.mbarrier::complete_tx::bytes [%0], [%1], %2, [%3];" ::"r"(dst), "l"(src), "r"(bytes), "r"(bar) : "memory");
}
__device__ __forceinline__ void bulk_ld_mc(uint32_t dst, const void* src, int bytes, uint32_t bar) {
  asm volatile("cp.async.bulk.shared::cluster.global.mbarrier::complete_tx::bytes.multicast::cluster [%0], [%1], %2, [%3], %4;"
               ::"r"(dst), "l"(src), "r"(bytes), "r"(bar), "h"((uint16_t)3) : "memory");
}
__device__ __forceinline__ void tma2d_st(const CUtensorMap* m, uint32_t src, int c0, int c1) {
  asm volatile("cp.async.bulk.tensor.2d.global.shared::cta.bulk_group [%0, {%2, %3}], [%1];" ::"l"(m), "r"(src), "r"(c0), "r"(c1) : "memory");
}
__device__ __forceinline__ void pf_l2(const void* p, int bytes) { asm volatile("cp.async.bulk.prefetch.L2.global [%0], %1;" ::"l"(p), "r"(bytes) : "memory"); }
__device__ __forceinline__ void pf_t2d(const CUtensorMap* m, int c0, int c1) {
  asm volatile("cp.async.bulk.prefetch.tensor.2d.L2.global [%0, {%1, %2}];" ::"l"(m), "r"(c0), "r"(c1) : "memory");
}
__device__ __forceinline__ void pf_t3d(const CUtensorMap* m, int c0, int c1, int c2) {
  asm volatile("cp.async.bulk.prefetch.tensor.3d.L2.global [%0, {%1, %2, %3}];" ::"l"(m), "r"(c0), "r"(c1), "r"(c2) : "memory");
}
__device__ __forceinline__ void ldsm4(uint32_t (&r)[4], uint32_t a) {
  asm volatile("ldmatrix.sync.aligned.m8n8.x4.shared.b16 {%0,%1,%2,%3}, [%4];" : "=r"(r[0]), "=r"(r[1]), "=r"(r[2]), "=r"(r[3]) : "r"(a) : "memory");
}
__device__ __forceinline__ void ldsm4t(uint32_t (&r)[4], uint32_t a) {
  asm volatile("ldmatrix.sync.aligned.m8n8.x4.trans.shared.b16 {%0,%1,%2,%3}, [%4];" : "=r"(r[0]), "=r"(r[1]), "=r"(r[2]), "=r"(r[3]) : "r"(a) : "memory");
}
__device__ __forceinline__ void stsm4(uint32_t a, uint32_t r0, uint32_t r1, uint32_t r2, uint32_t r3) {
  asm volatile("stmatrix.sync.aligned.m8n8.x4.shared.b16 [%0], {%1,%2,%3,%4};" ::"r"(a), "r"(r0), "r"(r1), "r"(r2), "r"(r3) : "memory");
}
__device__ __forceinline__ uint32_t pk2(float lo, float hi) { uint32_t r; asm("cvt.rn.bf16x2.f32 %0, %1, %2;" : "=r"(r) : "f"(hi), "f"(lo)); return r; }
__device__ __forceinline__ uint32_t hmul(uint32_t a, uint32_t b) { uint32_t r; asm("mul.rn.bf16x2 %0, %1, %2;" : "=r"(r) : "r"(a), "r"(b)); return r; }
__device__ __forceinline__ uint32_t hadd(uint32_t a, uint32_t b) { uint32_t r; asm("add.rn.bf16x2 %0, %1, %2;" : "=r"(r) : "r"(a), "r"(b)); return r; }
__device__ __forceinline__ uint32_t hmax(uint32_t a, uint32_t b) { uint32_t r; asm("max.bf16x2 %0, %1, %2;" : "=r"(r) : "r"(a), "r"(b)); return r; }
__device__ __forceinline__ uint32_t hmin(uint32_t a, uint32_t b) { uint32_t r; asm("min.bf16x2 %0, %1, %2;" : "=r"(r) : "r"(a), "r"(b)); return r; }
__device__ __forceinline__ uint32_t hmaxabs(uint32_t a, uint32_t b) { uint32_t r; asm("max.xorsign.abs.bf16x2 %0, %1, %2;" : "=r"(r) : "r"(a), "r"(b)); return r; }
__device__ __forceinline__ float ex2(float x) { float r; asm("ex2.approx.ftz.f32 %0, %1;" : "=f"(r) : "f"(x)); return r; }
__device__ __forceinline__ float rcp_fast(float x) { float r; asm("rcp.approx.ftz.f32 %0, %1;" : "=f"(r) : "f"(x)); return r; }
__device__ __forceinline__ uint32_t phi2(float lo, float hi) {
  uint32_t t;
  asm("cvt.rn.relu.bf16x2.f32 %0, %1, %2;" : "=r"(t) : "f"(hi), "f"(lo));
  const uint32_t e = pk2(ex2(lo * 1.4426950408889634f), ex2(hi * 1.4426950408889634f));
  return hadd(hadd(t, hmin(e, 0x3F803F80u)), 0x35863586u);
}
__device__ __forceinline__ bool opaque_true() { uint32_t v; asm volatile("mov.u32 %0, %%nctaid.y;" : "=r"(v)); return v != 0; }
__device__ __forceinline__ int normalise(uint32_t (&v)[32], float fd) {
  const float f0 = fd + __uint_as_float(v[0] << 16);
  uint32_t m[4] = {hmaxabs(__float_as_uint(f0) >> 16, v[0]), v[1], v[2], v[3]};
#pragma unroll
  for (int i = 4; i < 32; i++) m[i & 3] = hmaxabs(m[i & 3], v[i]);
  m[0] = hmaxabs(hmaxabs(m[0], m[1]), hmaxabs(m[2], m[3]));
  const int e = min(max((int)(__reduce_max_sync(~0u, max(m[0] & 0x7FFFu, (m[0] >> 16) & 0x7FFFu)) >> 7), 1), 253);
  if (e > 141) {
#pragma unroll
    for (int i = 0; i < 32; i++) v[i] = hmul(v[i], 0x07000700u);
  }
  const uint32_t sc = (e > 141 ? 255 - e : 142 - e) * 0x00800080u;
#pragma unroll
  for (int i = 0; i < 32; i++) {
    const uint32_t a = hmul(v[i], sc);
    v[i] = (a & 0x0FFF0FFFu) * 7 + a;
  }
  v[0] = __byte_perm(v[0], __half_as_ushort(__float2half_rn(f0 * __uint_as_float((254 - e) << 23))), 0x3254);
  return e;
}
__device__ __forceinline__ void poll_ge(const unsigned* p, unsigned target) {
#pragma unroll 1
  for (int n = 0; n < SPIN_LIMIT; n++) {
    unsigned v;
    asm volatile("ld.relaxed.gpu.global.u32 %0, [%1];" : "=r"(v) : "l"(p) : "memory");
    if (__all_sync(~0u, (int)(v - target) >= 0)) { asm volatile("fence.acquire.gpu;" ::: "memory"); return; }
  }
  __trap();
}

__device__ __forceinline__ bool elect_one() {
  uint32_t p;
  asm volatile("{\n.reg .pred p;\nelect.sync _|p, 0xffffffff;\nselp.u32 %0, 1, 0, p;\n}\n" : "=r"(p));
  return p;
}
__device__ __forceinline__ uint4 ld_nc4(const void* p) {
  uint4 v;
  asm volatile("ld.global.nc.L1::no_allocate.v4.u32 {%0,%1,%2,%3}, [%4];" : "=r"(v.x), "=r"(v.y), "=r"(v.z), "=r"(v.w) : "l"(p));
  return v;
}
__device__ __forceinline__ void st_cg4(void* p, uint4 v) {
  asm volatile("st.global.cg.v4.u32 [%0], {%1,%2,%3,%4};" ::"l"(p), "r"(v.x), "r"(v.y), "r"(v.z), "r"(v.w) : "memory");
}
__device__ __forceinline__ uint32_t mapa(uint32_t a, uint32_t cta) { uint32_t r; asm("mapa.shared::cluster.u32 %0, %1, %2;" : "=r"(r) : "r"(a), "r"(cta)); return r; }
__device__ __forceinline__ void st_async(uint32_t a, uint32_t v, uint32_t bar) {
  asm volatile("st.async.weak.shared::cluster.mbarrier::complete_tx::bytes.b32 [%0], %1, [%2];" ::"r"(a), "r"(v), "r"(bar) : "memory");
}
__device__ __forceinline__ void st_async4(uint32_t a, uint32_t x, uint32_t y, uint32_t z, uint32_t w, uint32_t bar) {
  asm volatile("st.async.weak.shared::cluster.mbarrier::complete_tx::bytes.v4.b32 [%0], {%1,%2,%3,%4}, [%5];" ::"r"(a), "r"(x), "r"(y), "r"(z), "r"(w), "r"(bar) : "memory");
}
__device__ __forceinline__ void tma3d_st(const CUtensorMap* m, uint32_t src, int c0, int c1, int c2) {
  asm volatile("cp.async.bulk.tensor.3d.global.shared::cta.bulk_group [%0, {%2, %3, %4}], [%1];" ::"l"(m), "r"(src), "r"(c0), "r"(c1), "r"(c2) : "memory");
}
__device__ __forceinline__ uint4 ld_rlx4(const void* p) {
  uint4 v;
  asm volatile("{\n.reg .b128 t;\n.reg .b64 a, b;\nld.relaxed.gpu.global.b128 t, [%4];\nmov.b128 {a, b}, t;\nmov.b64 {%0, %1}, a;\nmov.b64 {%2, %3}, b;\n}\n"
               : "=r"(v.x), "=r"(v.y), "=r"(v.z), "=r"(v.w) : "l"(p) : "memory");
  return v;
}
__device__ __forceinline__ void ld_stale4(uint4& v, const void* p, uint32_t tag) {
  asm volatile("{\n.reg .b128 t;\n.reg .b64 a, b;\n.reg .b32 x;\n.reg .pred p;\n"
               "lop3.b32 x, %0, %5, 1, 0x28;\nsetp.ne.u32 p, x, 0;\n"
               "mov.b64 a, {%0, %1};\nmov.b64 b, {%2, %3};\nmov.b128 t, {a, b};\n"
               "@p ld.relaxed.gpu.global.b128 t, [%4];\n"
               "mov.b128 {a, b}, t;\nmov.b64 {%0, %1}, a;\nmov.b64 {%2, %3}, b;\n}\n"
               : "+r"(v.x), "+r"(v.y), "+r"(v.z), "+r"(v.w) : "l"(p), "r"(tag) : "memory");
}
__device__ __forceinline__ void st_tag4(void* p, float a, float b, float c, float d, uint32_t tag) {
  asm volatile("{\n.reg .b128 t;\n.reg .b64 a, b;\nmov.b64 a, {%1, %2};\nmov.b64 b, {%3, %4};\nmov.b128 t, {a, b};\nst.relaxed.gpu.global.b128 [%0], t;\n}\n"
               ::"l"(p), "r"((__float_as_uint(a) & ~1u) | tag), "f"(b), "f"(c), "f"(d) : "memory");
}
__device__ __forceinline__ uint32_t stale8(const uint4 (&f)[8], uint32_t tag) {
  uint32_t r[4];
#pragma unroll
  for (int i = 0; i < 4; i++) asm("lop3.b32 %0, %1, %2, %3, 0x7E;" : "=r"(r[i]) : "r"(f[2 * i].x), "r"(f[2 * i + 1].x), "r"(tag));
  asm("lop3.b32 %0, %0, %1, %2, 0xFE;" : "+r"(r[0]) : "r"(r[1]), "r"(r[2]));
  return r[0] | r[3];
}

struct ConvC { uint32_t a1[2][4], wa[2], wb[2], sg; };
__device__ __forceinline__ uint64_t dsc(uint32_t lo, uint32_t hi) { return ((uint64_t)hi << 32) | lo; }
__device__ __forceinline__ uint32_t hfma(uint32_t a, uint32_t b, uint32_t c) { uint32_t r; asm("fma.rn.f16x2 %0, %1, %2, %3;" : "=r"(r) : "r"(a), "r"(b), "r"(c)); return r; }
__device__ __forceinline__ uint32_t hfnma(uint32_t a, uint32_t b, uint32_t c) { uint32_t r; asm("{.reg .b32 n; neg.f16x2 n, %1; fma.rn.f16x2 %0, n, %2, %3;}" : "=r"(r) : "r"(a), "r"(b), "r"(c)); return r; }
__device__ __forceinline__ uint32_t hmul16(uint32_t a, uint32_t b) { uint32_t r; asm("mul.rn.f16x2 %0, %1, %2;" : "=r"(r) : "r"(a), "r"(b)); return r; }
template <int N> __device__ __forceinline__ void keepu(uint32_t (&d)[N]) {
#pragma unroll
  for (int i = 0; i < N; i++) asm volatile("" : "+r"(d[i])::"memory");
}
__device__ __forceinline__ void conv_m1(const ConvC& K, uint32_t (&u)[16], uint32_t l) {
  wg_fence();
  wgmma_hrs_n64<1>(u, K.a1[0][0], K.a1[0][1], K.a1[0][2], K.a1[0][3], dsc(l, 32), 0);
  wgmma_hrs_n64<1>(u, K.a1[1][0], K.a1[1][1], K.a1[1][2], K.a1[1][3], dsc(l + 16, 32), 1);
  wg_commit();
}
__device__ __forceinline__ void conv_s2(const ConvC& K, uint32_t (&u)[16], uint32_t (&Z)[2][8], uint32_t dfl) {
  uint32_t fr[8], fi[8];
#pragma unroll
  for (int c = 0; c < 8; c++) {
    const uint32_t r = hfma(K.wa[c & 1], u[2 * c + 1], u[2 * c]);
    fi[c] = hfma(K.wb[c & 1], r, u[2 * c + 1]);
    fr[c] = hfma(K.wa[c & 1], fi[c], r);
  }
  wg_fence();
#pragma unroll
  for (int p = 0; p < 2; p++) {
    wgmma_hrs_n32<0>(Z[p], fr[4 * p], fr[4 * p + 2], fr[4 * p + 1], fr[4 * p + 3], dsc(dfl, 32), 0);
    wgmma_hrs_n32<0>(Z[p], fi[4 * p], fi[4 * p + 2], fi[4 * p + 1], fi[4 * p + 3], dsc(dfl + 16, 32), 1);
  }
  wg_commit();
}
__device__ __forceinline__ void conv_win(const ConvC& K, const uint32_t (&X)[2][8], uint32_t (&W)[2][8]) {
#pragma unroll
  for (int b = 0; b < 4; b++)
#pragma unroll
    for (int c = 0; c < 2; c++) {
      const uint32_t xr = X[b >> 1][2 * c + (b & 1)], xi = X[b >> 1][4 + 2 * c + (b & 1)];
      const int a = b ? b - 1 : 0;
      W[b >> 1][2 * c + (b & 1)] = b ? hfnma(K.sg, X[a >> 1][4 + 2 * c + (a & 1)], xr) : hmul16(xr, 0x3C003C00u);
      W[b >> 1][4 + 2 * c + (b & 1)] = b ? hfma(K.sg, X[a >> 1][2 * c + (a & 1)], xi) : hmul16(xi, 0x3C003C00u);
    }
}
template <int p>
__device__ __forceinline__ void conv_pw(uint32_t (&X)[2][8], uint32_t (&H)[2][8], uint32_t (&V)[8], uint32_t dil) {
  uint32_t pr[2][2], pi[2][2];
#pragma unroll
  for (int jj = 0; jj < 2; jj++)
#pragma unroll
    for (int c = 0; c < 2; c++) {
      const int j = 2 * p + jj;
      uint32_t sr = 0, si = 0;
#pragma unroll
      for (int a = 0; a <= j; a++) {
        const int b = j - a;
        const uint32_t hr = H[a >> 1][2 * c + (a & 1)], hi = H[a >> 1][4 + 2 * c + (a & 1)];
        const uint32_t xr = X[b >> 1][2 * c + (b & 1)], xi = X[b >> 1][4 + 2 * c + (b & 1)];
        sr = a == 0 ? hmul16(hr, xr) : hfma(hr, xr, sr);
        si = a == 0 ? hmul16(hr, xi) : hfma(hr, xi, si);
        sr = hfnma(hi, xi, sr);
        si = hfma(hi, xr, si);
      }
      pr[jj][c] = sr; pi[jj][c] = si;
    }
  wg_fence();
  wgmma_hrs_n32<0>(V, pr[0][0], pr[1][0], pr[0][1], pr[1][1], dsc(dil, 32), 0);
  wgmma_hrs_n32<0>(V, pi[0][0], pi[1][0], pi[0][1], pi[1][1], dsc(dil + 16, 32), 1);
  wg_commit();
}
template <int p>
__device__ __forceinline__ void conv_it(const ConvC& K, uint32_t (&V)[8], uint32_t vst) {
#pragma unroll
  for (int jj = 0; jj < 2; jj++) {
    uint32_t wr[2], wi[2];
#pragma unroll
    for (int c = 0; c < 2; c++) {
      const uint32_t r = hfnma(K.wa[c], V[4 + 2 * c + jj], V[2 * c + jj]);
      wi[c] = hfnma(K.wb[c], r, V[4 + 2 * c + jj]);
      wr[c] = hfnma(K.wa[c], wi[c], r);
    }
    stsm4(vst + (2 * p + jj) * 2048, wr[0], wr[1], wi[0], wi[1]);
  }
}
__device__ __forceinline__ void conv_m4(uint32_t (&y)[8], uint32_t (&a)[4][4], uint32_t d4l) {
  wg_fence();
  wgmma_hrs_n32<0>(y, a[0][0], a[0][1], a[0][2], a[0][3], dsc(d4l, 64), 0);
#pragma unroll
  for (int s = 1; s < 4; s++) wgmma_hrs_n32<0>(y, a[s][0], a[s][1], a[s][2], a[s][3], dsc(d4l + s * 16, 64), 1);
  wg_commit();
}

struct Params {
  CUtensorMap tmX, tmW, tmWo, tmWo1, tmK, tmV, tmQ, tmOA, tmOB;
  const __nv_bfloat16 *shift_k, *h, *D, *x, *w, *wo, *q;
  float *part, *kv;
  uint4* o;
  unsigned *ocnt, *epoch;
  const uint32_t *thr, *img;
};

__global__ void __cluster_dims__(2, 1, 1) __launch_bounds__(384, 1) fused_kernel(const __grid_constant__ Params P) {
  extern __shared__ __align__(1024) uint8_t smem[];
  const uint32_t sb = smem_u32(smem);
  const uint32_t bars = sb + OFF_BAR;
  const int tid = threadIdx.x, lane = tid & 31;
  const int warp = __shfl_sync(~0u, tid >> 5, 0);
  const int rank = blockIdx.x & 1, cl = blockIdx.x >> 1;
  const int mb = cl >> 3, hq = cl & 7;
  const int hp = 2 * hq + rank;
  const int rb = 2 * mb + (hq >> 2), cb = hq & 3;
#define BAR(i) (bars + 8 * (i))

  if (tid == 0) { STAMP(0, 0); GSTAMP(0, 30); }
  if (warp == 8) {
    if (elect_one()) {
      mbar_init(BAR(B_FULL1), 1);
      asm volatile("fence.mbarrier_init.release.cluster;" ::: "memory");
      mbar_expect(BAR(B_FULL1), STAGE_BYTES);
      tma3d(sb + 32768, &P.tmW, hp * 64, 0, 0, BAR(B_FULL1));
    }
    if (lane == 0) STAMP(3, 21);
  } else if (lane == 0) {
    const int wi = warp - (warp > 8);
#pragma unroll
    for (int r = 0; r < 6; r++)
      if (r < 5 || wi < B_COUNT - 56) mbar_init(BAR(1 + 11 * r + wi), ((uint32_t)(bar_counts(r) >> (4 * wi)) & 15) + 1);
    asm volatile("fence.mbarrier_init.release.cluster;" ::: "memory");
  }
  if (tid == 0) STAMP(2, 6);
  asm volatile("barrier.cluster.arrive.relaxed.aligned;\nbarrier.cluster.wait.aligned;" ::: "memory");
  if (warp == 8 && elect_one()) tma2d_mc(sb + rank * 16384, &P.tmX, 0, mb * 256 + rank * 128, BAR(B_FULL1));
  if (tid == 256) STAMP(2, 7);

  if (warp < 8) {
    asm volatile("setmaxnreg.inc.sync.aligned.u32 224;");
    const int wg = warp >> 2, w = warp & 3, g = lane >> 2, q = lane & 3, t = tid & 127;
    const bool elect = (t == 0);
    const uint32_t s16 = (sb & 0x3FFFF) >> 4;
    constexpr uint32_t SW128 = 64 | (1u << 30);
    uint32_t pq[2][16], v[32];
    int ehs;
    ConvC K;
    {
      float acc[2][96];
      int st = 0, ph = 0;
#pragma unroll 1
      for (int kb = 0; kb < 14; kb++) {
        mbar_wait(BAR(B_FULL1 + st), ph);
        if (kb == 0 && elect) { STAMP(wg, 1); GSTAMP(wg, 26); }
        if (kb == 8 && elect) { STAMP(wg, 16); GSTAMP(wg, 25); }
        if (tid == 0) STAMP(2, 8 + kb);
        const uint32_t da = s16 + st * (STAGE_BYTES >> 4) + wg * 1024 + (1 << 16);
        const uint32_t db = s16 + st * (STAGE_BYTES >> 4) + 2048 + (512 << 16);
        wg_fence();
#pragma unroll
        for (int ks = 0; ks < 4; ks++) {
          wgmma_ss_n192<0, 1>(acc[0], dsc(da + ks * 2, SW128), dsc(db + ks * 128, SW128), (kb | ks) != 0);
          wgmma_ss_n192<0, 1>(acc[1], dsc(da + 512 + ks * 2, SW128), dsc(db + ks * 128, SW128), (kb | ks) != 0);
        }
        wg_commit();
        wg_wait<1>();
        if (kb > 0 && t < 2) mbar_arrive_cl(BAR(B_EMPTY1 + (st == 0 ? 2 : st - 1)), t);
        if (++st == 3) { st = 0; ph ^= 1; }
      }
#define TAIL_MMA(mt, stage) do { wg_fence(); _Pragma("unroll") for (int ks = 0; ks < 4; ks++) \
        wgmma_ss_n192<0, 1>(acc[mt], dsc(s16 + (stage) * (STAGE_BYTES >> 4) + wg * 1024 + (mt) * 512 + (1 << 16) + ks * 2, SW128), \
                            dsc(s16 + (stage) * (STAGE_BYTES >> 4) + 2048 + (512 << 16) + ks * 128, SW128), 1); wg_commit(); } while (0)
      mbar_wait(BAR(B_FULL1 + 2), 0);
      TAIL_MMA(0, 2);
      wg_wait<1>();
      if (t < 2) mbar_arrive_cl(BAR(B_EMPTY1 + 1), t);
      mbar_wait(BAR(B_FULL1 + 0), 1);
      TAIL_MMA(0, 0);
      TAIL_MMA(1, 2);
      if (!TSPLIT) TAIL_MMA(1, 0);
      const uint32_t lrow = sb + (16 * w + 8 * ((lane >> 3) & 1) + (lane & 7)) * 128 + (((lane >> 4) ^ (lane & 7)) << 4);
      const uint32_t pko = OFF_H + wg * 8192, vo0 = 6 * 16384 + wg * 8192, vo1 = 7 * 16384 + wg * 16384;
#define E1K(mt, i) do { if (opaque_true()) { _Pragma("unroll") for (int j = (i); j < (i) + 2; j++) { \
          const float* a = &acc[mt][32 + 8 * j]; const float* b = a + 32; const uint32_t o = lrow ^ (j * 32); \
          stsm4(o + ((mt) ? vo1 : vo0), pk2(b[0], b[1]), pk2(b[2], b[3]), pk2(b[4], b[5]), pk2(b[6], b[7])); \
          stsm4(o + pko + (mt) * 16384, phi2(a[0], a[1]), phi2(a[2], a[3]), phi2(a[4], a[5]), phi2(a[6], a[7])); } } } while (0)
#define E1Q(mt) do { if (opaque_true()) { _Pragma("unroll") for (int i = 0; i < 16; i++) pq[mt][i] = phi2(acc[mt][2 * i], acc[mt][2 * i + 1]); } } while (0)
      const uint4* hp4 = (const uint4*)(P.h + (blockIdx.x * 8 + warp) * 2048) + ((lane & 15) * 2 + (lane >> 4));
#define LOAD_H(i0, i1) do { _Pragma("unroll") for (int i = (i0); i < (i1); i++) { \
        const uint4 u = ld_nc4(hp4 + i * 32); v[4 * i] = u.x; v[4 * i + 1] = u.y; v[4 * i + 2] = u.z; v[4 * i + 3] = u.w; } } while (0)
      mbar_wait(BAR(B_EMPTY1 + 1), 0);
      if (TSPLIT) wg_wait<1>(); else wg_wait<2>();
      keep(acc[0]);
      if (elect) STAMP(wg, 18);
      E1K(0, 0);
      if (TSPLIT) TAIL_MMA(1, 0);
      LOAD_H(0, HL1);
      E1K(0, 2);
      if (elect) STAMP(wg, 19);
      LOAD_H(HL1, 8);
      if (QPOS == 0) E1Q(0);
      if (elect) STAMP(wg, 20);
      {
        const uint4* ct = (const uint4*)P.thr + t;
#pragma unroll
        for (int s = 0; s < 2; s++) { const uint4 u = ld_nc4(ct + s * 128); K.a1[s][0] = u.x; K.a1[s][1] = u.y; K.a1[s][2] = u.z; K.a1[s][3] = u.w; }
        const uint4 u = ld_nc4(ct + 2 * 128);
        K.wa[0] = u.x; K.wa[1] = u.y; K.wb[0] = u.z; K.wb[1] = u.w;
        K.sg = (lane & 4) ? 0xBC00BC00u : 0x3C003C00u;
      }
      mbar_wait(BAR(B_XT), 0);
      const uint32_t tag = ~*(volatile unsigned*)(smem + OFF_EPOCH) & 1;
      wg_wait<0>();
      keep(acc[1]);
      if (t < 2) mbar_arrive_cl(BAR(B_EMPTY1 + 0), t);
      if (elect) { STAMP(wg, 2); GSTAMP(wg, 27); }
      E1K(1, 0);
      E1K(1, 2);
      fence_async();
      bar_sync(1 + wg);
      if (elect) STAMP(wg, 3);
      float kva[36];
      wg_fence();
#pragma unroll
      for (int ks = 0; ks < 8; ks++) {
        const uint32_t vb = ((ks >> 2 ? vo1 : vo0) >> 4) + (ks & 3) * 128;
        wgmma_ss_n72<1, 1>(kva, dsc(s16 + (pko >> 4) + (ks >> 2) * 1024 + (ks & 3) * 128 + (1 << 16), SW128),
                           dsc(s16 + vb + (((OFF_ONES >> 4) - vb) << 16), SW128), ks != 0);
      }
      wg_commit();
      int eh = 0;
      if (QPOS == 1) E1Q(0);
      if (NPOS == 0) eh = normalise(v, lane == 0 ? *(const float*)(smem + OFF_D + 4 * warp) : 0.f);
      wg_wait<0>();
      keep(kva);
      if (elect) STAMP(wg, 24);
      {
        float4 p[5];
#pragma unroll
        for (int c = 0; c < 4; c++)
          p[c] = w < 2 ? make_float4(kva[4 * c], kva[4 * c + 1], kva[4 * c + 2], kva[4 * c + 3])
                       : make_float4(kva[16 + 4 * c], kva[17 + 4 * c], kva[18 + 4 * c], kva[19 + 4 * c]);
        p[4] = make_float4(kva[32], kva[34], __shfl_down_sync(~0u, kva[32], 4), __shfl_down_sync(~0u, kva[34], 4));
        float4* hand = (float4*)(smem + 8 * 16384 + 8192 - (w >> 1) * 16384) + (t & 63);
        if ((w >> 1) != wg) {
#pragma unroll
          for (int c = 0; c < 5; c++) hand[c * 64] = p[c];
          asm volatile("bar.arrive %0, 128;" ::"r"(5 + (w >> 1)) : "memory");
        } else {
          float* dst = P.part + (hp * 8 + mb) * 2176;
          asm volatile("bar.sync %0, 128;" ::"r"(5 + (w >> 1)) : "memory");
#pragma unroll
          for (int c = 0; c < 5; c++) { const float4 u = hand[c * 64]; p[c].x += u.x; p[c].y += u.y; p[c].z += u.z; p[c].w += u.w; }
#pragma unroll
          for (int c = 0; c < 5; c++)
            if (c < 4 || !(lane & 7)) st_tag4(c < 4 ? dst + (c * 128 + t) * 4 : dst + 2048 + 16 * w + 2 * g, p[c].x, p[c].y, p[c].z, p[c].w, tag);
        }
        __syncwarp();
        if (lane == 0) mbar_arrive(BAR(B_PKFREE));
      }
      if (elect) STAMP(wg, 4);
      if (QPOS == 2) E1Q(0);
      E1Q(1);
      if (NPOS == 1) eh = normalise(v, lane == 0 ? *(const float*)(smem + OFF_D + 4 * warp) : 0.f);
      ehs = eh;
    }
    mbar_wait(BAR(B_PKFREE), 0);
    if (elect) STAMP(wg, 17);
    {
      const int e = ehs;
      uint8_t* dst = smem + OFF_H + (w & 2) * 8192 + wg * 8192 + (w & 1) * 4096 + (lane >> 4) * 512 + (lane & 15) * 16;
#pragma unroll
      for (int i = 0; i < 8; i++)
        *(uint4*)(dst + (i >> 1) * 1024 + (i & 1) * 256) = make_uint4(v[4 * i], v[4 * i + 1], v[4 * i + 2], v[4 * i + 3]);
      if (lane < 2) st_async(mapa(sb + OFF_SCALE + (8 * rank + warp) * 4, lane), min(max(e + smem[OFF_EX + warp] - 124, 1), 254) << 23, mapa(BAR(B_Y), lane));
      fence_async();
      bar_sync(1 + wg);
    }
    if (elect) STAMP(wg, 5);
    {
      const uint32_t dfl = s16 + (OFF_F2F >> 4) + (8 << 16), dil = s16 + (OFF_F2I >> 4) + (8 << 16), d4l = s16 + (OFF_F4 >> 4) + (8 << 16);
      const uint32_t xl = s16 + (OFF_XT >> 4) + 4 * wg * (XT_STRIDE >> 4) + (8 << 16);
      const uint32_t hl = s16 + (OFF_H >> 4) + wg * 512 + (8 << 16);
      uint32_t vst = sb + wg * 8192 + w * 512 + lane * 16, vld = sb + wg * 8192 + w * 2048 + lane * 16;
      uint32_t ya = mapa(sb + OFF_XT + 4 * wg * XT_STRIDE + (2 * rank + (w & 1)) * 1024 + lane * 16, w >> 1);
      const uint32_t ybar = mapa(BAR(B_Y), w >> 1);
      asm volatile("" : "+r"(vst), "+r"(vld), "+r"(ya));
      uint32_t ux[16], uh[16], W[2][8], V0[8], V1[8], y[8], a[4][4];
      uint4 ov[4];
      uint4* const ot = P.o + ((2 * mb + wg) * 16 + hq) * 1024 + (16 * w + g) * 8 + ((4 * rank + q) ^ g);
#define YOUT(i) do { mbar_wait(BAR(B_XFREE + 4 * wg + (i)), 0); \
        st_async4(ya + (i) * XT_STRIDE, y[0], y[2], y[4], y[6], ybar); \
        st_async4(ya + (i) * XT_STRIDE + 512, y[1], y[3], y[5], y[7], ybar); } while (0)
      auto ocalc = [&]() {
        wg_wait<0>();
        if (elect) STAMP(wg, 8);
        mbar_wait(BAR(B_KV), 0);
        if (elect) STAMP(wg, 9);
        float oa[4][20];
        wg_fence();
#pragma unroll
        for (int m = 0; m < 8; m++) {
          const uint32_t* p = &pq[m >> 2][4 * (m & 3)];
          wgmma_rs_n40<1>(oa[m >> 1], p[0], p[1], p[2], p[3], dsc(s16 + (OFF_KVB >> 4) + ((m >> 1) & 1) * 160 + (m & 1) * 16 + (8 << 16), 32), m & 1);
        }
        wg_commit();
        wg_wait<0>();
#pragma unroll
        for (int m = 0; m < 4; m++) {
          float (&o)[20] = oa[2 * (m & 1) + (m >> 1)];
          keep(o);
          const uint32_t den = hadd(pk2(o[16], o[18]), 0x35863586u);
#pragma unroll
          for (int r = 0; r < 2; r++) {
            const float ri = rcp_fast(__uint_as_float(r ? (den & 0xFFFF0000u) : (den << 16)));
            uint4 u;
            u.x = pk2(o[2 * r] * ri, o[2 * r + 1] * ri);
            u.y = pk2(o[4 + 2 * r] * ri, o[5 + 2 * r] * ri);
            u.z = pk2(o[8 + 2 * r] * ri, o[9 + 2 * r] * ri);
            u.w = pk2(o[12 + 2 * r] * ri, o[13 + 2 * r] * ri);
            if (m < 2) st_cg4(ot + (64 * m + 8 * r) * 8, u); else ov[2 * (m & 1) + r] = u;
          }
          if (m == 1) { __syncwarp(); if (lane == 0) mbar_arrive(BAR(B_ODONE)); }
        }
        if (elect) STAMP(wg, 10);
      };
      auto ostore1 = [&]() {
#pragma unroll
        for (int m = 0; m < 4; m++) st_cg4(ot + 8 * 1024 + (64 * (m >> 1) + 8 * (m & 1)) * 8, ov[m]);
        __syncwarp();
        if (lane == 0) mbar_arrive(BAR(B_ODONE1));
      };
      uint32_t X[4][2][8], H[4][2][8];
      conv_m1(K, ux, xl);
      conv_m1(K, uh, hl);
      wg_wait<1>(); keepu(ux);
      if (lane == 0) mbar_arrive_cl(BAR(B_XFREE + 4 * wg), rank ^ 1);
      conv_s2(K, ux, X[0], dfl);
      wg_wait<1>(); keepu(uh);
      conv_s2(K, uh, H[0], dfl);
#pragma unroll
      for (int i = 0; i < 4; i++) {
        const bool nx = i < 3;
        const int n = nx ? i + 1 : i;
        const uint32_t vo = (i & 1) ? OFF_H + (i >> 1) * 16384 : OFF_VP;
        if (2 * i == OCH) ocalc();
        if (2 * i == OCH + O1D) ostore1();
        if (nx) {
          conv_m1(K, ux, xl + n * (XT_STRIDE >> 4));
          conv_m1(K, uh, hl + (n >> 1) * 1024 + (n & 1) * 256);
        }
        if (2 * i != OCH) { if (nx) { if (i > 0) wg_wait<3>(); else wg_wait<2>(); } else wg_wait<1>(); }
        keepu(X[i][0]); keepu(X[i][1]); keepu(H[i][0]); keepu(H[i][1]);
        conv_win(K, X[i], W);
        conv_pw<0>(W, H[i], V0, dil);
        conv_pw<1>(W, H[i], V1, dil);
        wg_wait<2>();
        if (i > 0) { keepu(y); YOUT(i - 1); }
        if (2 * i + 1 == OCH) ocalc();
        if (2 * i + 1 == OCH + O1D) ostore1();
        if (nx) {
          keepu(ux); keepu(uh);
          if (lane == 0) mbar_arrive_cl(BAR(B_XFREE + 4 * wg + n), rank ^ 1);
          conv_s2(K, ux, X[n], dfl);
          wg_wait<1>();
        } else wg_wait<0>();
        keepu(V0); keepu(V1);
        conv_it<0>(K, V0, vst + vo);
        conv_it<1>(K, V1, vst + vo);
        bar_sync(1 + wg);
#pragma unroll
        for (int s = 0; s < 4; s++) ldsm4t(a[s], vld + vo + s * 512);
        if (nx) conv_s2(K, uh, H[n], dfl);
        conv_m4(y, a, d4l);
        if (i > 0 && lane < 2) mbar_arrive_cl(BAR(B_AFREE + i - 1), lane);
        if (elect && i < 3) STAMP(wg, i < 2 ? 6 + i : 9 + i);
      }
      wg_wait<0>(); keepu(y);
      YOUT(3);
      if (lane == 0) mbar_arrive(BAR(B_Y));
      if (elect) STAMP(wg, 12);
    }
    {
      float acc[64];
#pragma unroll 1
      for (int kb = 0; kb < 16; kb++) {
        mbar_wait(BAR(B_FULL2 + kb), 0);
        if (kb == 0 && elect) { STAMP(wg, 13); GSTAMP(wg, 28); }
        const uint32_t da = s16 + ((uint32_t)(SLOT_A >> (4 * kb)) & 15) * 1024 + wg * 512 + (1 << 16);
        const uint32_t db = s16 + ((uint32_t)(SLOT_B >> (4 * kb)) & 15) * 1024 + (512 << 16);
        wg_fence();
#pragma unroll
        for (int ks = 0; ks < 4; ks++) wgmma_ss_n128<0, 1>(acc, dsc(da + ks * 2, SW128), dsc(db + ks * 128, SW128), (kb | ks) != 0);
        wg_commit();
        wg_wait<1>();
        if (kb > 0 && kb < 14 && t < 2 && (kb <= 11 || t == rank)) mbar_arrive_cl(BAR(B_CONS2 + kb - 1), t);
      }
      wg_wait<0>();
      keep(acc);
      if (elect) { STAMP(wg, 14); GSTAMP(wg, 29); }
      mbar_wait(BAR(B_CONS2 + 12), 0);
      const uint32_t stg = sb + (wg ? 5 : 0) * 16384;
      const uint32_t lrow = stg + (16 * w + 8 * ((lane >> 3) & 1) + (lane & 7)) * 128 + (((lane >> 4) ^ (lane & 7)) << 4);
#pragma unroll
      for (int cp = 0; cp < 8; cp++) {
        const float* a = &acc[8 * cp];
        stsm4((lrow ^ ((cp & 3) * 32)) + (cp >> 2) * 8192, pk2(a[0], a[1]), pk2(a[2], a[3]), pk2(a[4], a[5]), pk2(a[6], a[7]));
      }
      fence_async();
      bar_sync(1 + wg);
      if (elect) {
        const int col = 1024 + 256 * cb + 128 * rank, row = 128 * rb + 64 * wg;
        tma2d_st(&P.tmOB, stg, col, row);
        tma2d_st(&P.tmOB, stg + 8192, col + 64, row);
        asm volatile("cp.async.bulk.commit_group;\ncp.async.bulk.wait_group.read 0;" ::: "memory");
        STAMP(wg, 15); GSTAMP(wg, 31); PDUMP(wg);
      }
    }
  } else {
    asm volatile("setmaxnreg.dec.sync.aligned.u32 56;");
    if (warp == 8) {
      if (lane == 0) STAMP(3, 20);
      int st = 1, ph = 1;
      const uint8_t* pfx = (const uint8_t*)P.x + (mb * 256 + hp * 16 + (lane & 15)) * 2048;
      const uint8_t* pfw = (const uint8_t*)P.w + (mb * 8 + (lane & 7)) * 6144 + (lane >> 3) * 2048 + hp * 128;
#pragma unroll 1
      for (int kb = 1; kb < 16; kb++) {
        if (kb >= 3) mbar_wait(BAR(B_EMPTY1 + st), ph);
        const uint32_t sa = sb + st * STAGE_BYTES;
        if (elect_one()) {
          mbar_expect(BAR(B_FULL1 + st), STAGE_BYTES);
          tma2d_mc(sa + rank * 16384, &P.tmX, kb * 64, mb * 256 + rank * 128, BAR(B_FULL1 + st));
          tma3d(sa + 32768, &P.tmW, hp * 64, kb * 64, 0, BAR(B_FULL1 + st));
        }
        if (kb == 1 && lane == 0) STAMP(2, 24);
        if (PFD && kb >= 2) {
#pragma unroll 1
          for (int j = kb == 2 ? 3 : kb + PFD; j <= kb + PFD && j < 16; j++) {
            if (lane < 16) asm volatile("prefetch.global.L2 [%0];" ::"l"(pfx + j * 128));
            if (lane < 24) asm volatile("prefetch.global.L2 [%0];" ::"l"(pfw + j * (64 * 6144)));
          }
          if (kb >= QPF && kb < QPF + 8) asm volatile("prefetch.global.L2 [%0];" ::"l"((const uint8_t*)P.q + (blockIdx.x * 256 + (kb - QPF) * 32 + lane) * 128));
          if (kb >= 4)
            asm volatile("prefetch.global.L2 [%0];" ::"l"(kb < 12 ? (const uint8_t*)P.h + (blockIdx.x * 256 + (kb - 4) * 32 + lane) * 128
                                                                  : (const uint8_t*)P.wo + (blockIdx.x * 128 + (kb - 12) * 32 + lane) * 128));
        }
        if (++st == 3) { st = 0; ph ^= 1; }
      }
      if (lane == 0) STAMP(2, 1);
      const unsigned epoch = P.epoch[blockIdx.x];
#define SLOT(tab, kb) (sb + ((uint32_t)((tab) >> (4 * (kb))) & 15) * 16384)
#define LOAD_B(kb) tma4d(SLOT(SLOT_B, kb), &P.tmWo, 0, ((kb) >> 3) * 32, 2 * ((kb) & 7), 4 * cb + 2 * rank, BAR(B_FULL2 + (kb)))
#define LOAD_A(kb) bulk_ld_mc(SLOT(SLOT_A, kb) + rank * 8192, P.o + (rb * 16 + (kb)) * 1024 + rank * 512, 8192, BAR(B_FULL2 + (kb)))
      mbar_wait(BAR(B_EMPTY1 + 0), 1);
      {
        const uint32_t c0 = clock();
#pragma unroll 1
        for (int i = 0; i < 14; i++) {
          const int kb = i >> 1;
          if (i == 8) mbar_wait(BAR(B_PKFREE), 0);
          while (__any_sync(~0u, (uint32_t)clock() - c0 < i * BPACE)) __nanosleep(32);
          if (elect_one()) {
            if (!(i & 1)) mbar_expect(BAR(B_FULL2 + kb), 16384);
            tma4d(SLOT(SLOT_B, kb) + (i & 1) * 8192, &P.tmWo1, 0, 0, 2 * kb, 4 * cb + 2 * rank + (i & 1), BAR(B_FULL2 + kb));
            if (i == 0) mbar_expect(BAR(B_Q), 8192);
            if (i < 4) tma3d(sb + OFF_SPARE + 2048 * i, &P.tmQ, 16 * cl, 64 * rank + 32 * (i >> 1), 2 * ((i + 6) & 7), BAR(B_Q));
          }
        }
      }
      if (lane == 0) STAMP(2, 2);
      mbar_wait(BAR(B_AFREE), 0);
      if (elect_one()) mbar_expect(BAR(B_FULL2), 16384);
      {
        const uint32_t dst = SLOT(SLOT_A, 0) + rank * 8192;
        const uint4* src = P.o + rb * 16 * 1024 + rank * 512;
        poll_ge(&P.ocnt[rb * 32], 16 * (epoch + 1));
        asm volatile("fence.proxy.async.global;" ::: "memory");
        if (lane == 0) STAMP(2, 3);
        if (elect_one()) bulk_ld_mc(dst, src, 8192, BAR(B_FULL2));
        if (lane == 0) STAMP(3, 23);
      }
#pragma unroll 1
      for (int kb = 1; kb < 7; kb++) {
        mbar_wait(BAR(kb < 3 ? B_AFREE + kb : B_CONS2 + ((kb - 3) >> 1)), 0);
        if (elect_one()) { mbar_expect(BAR(B_FULL2 + kb), 16384); LOAD_A(kb); }
      }
#pragma unroll 1
      for (int kb = 7; kb < 16; kb++) {
        mbar_wait(BAR(B_CONS2 + kb - 5), 0);
        if (kb == 8) mbar_wait(BAR(B_O1RDY), 0);
        if (elect_one()) { mbar_expect(BAR(B_FULL2 + kb), 32768); LOAD_A(kb); LOAD_B(kb); }
      }
      if (lane == 0) { P.epoch[blockIdx.x] = epoch + 1; STAMP(2, 5); PDUMP(2); }
    } else {
      const uint32_t clk0 = clock();
      const int hw = warp - 9, g = lane >> 2, q = lane & 3;
      const unsigned epoch = P.epoch[blockIdx.x];
      const uint32_t tag = ~epoch & 1;
      const uint32_t stg = sb + OFF_STG + hw * STG_STRIDE, sbar = BAR(B_STG + 2 * hw);
      int ph = 0;
      {
        uint32_t tap[2][4];
#pragma unroll
        for (int cg = 0; cg < 2; cg++) {
          const uint2 u = __ldg((const uint2*)(P.shift_k + (16 * cl + 8 * cg + g) * 4));
          tap[cg][0] = __byte_perm(u.x, 0, 0x1010); tap[cg][1] = __byte_perm(u.x, 0, 0x3232);
          tap[cg][2] = __byte_perm(u.y, 0, 0x1010); tap[cg][3] = __byte_perm(u.y, 0, 0x3232);
        }
        if (hw == 0 && lane < 8) *(float*)(smem + OFF_D + 4 * lane) = __bfloat162float(P.D[blockIdx.x * 8 + lane]);
        if (hw == 1) asm volatile("prefetch.global.L2 [%0];" ::"l"(P.thr + (lane + 32 * (blockIdx.x & 1)) * 32));
        if (hw == 0 && elect_one()) {
          *(volatile unsigned*)(smem + OFF_EPOCH) = epoch;
          mbar_expect(BAR(B_XRAW), 32768);
          mbar_expect(BAR(B_Y), 32768 + 64);
        }
        for (int i = hw * 32 + lane; i < 528; i += 96) st_tag4(P.part + (hp * 8 + mb) * 2176 + 4 * i, 0.f, 0.f, 0.f, 0.f, tag ^ 1);
        if (hw < 2 || lane < 2) st_tag4(P.kv + hp * 2176 + (4 * (hw < 2 ? 64 * mb + 32 * hw + lane : 512 + 2 * mb + lane)), 0.f, 0.f, 0.f, 0.f, tag ^ 1);
        if (lane == 0) STAMP(3, hw);
        const uint32_t xo = sb + OFF_XT + g * XT_STRIDE + rank * 2048 + q * 4;
        const int krow = 8 + (lane & 7) - (lane >> 3);
        const uint32_t ka = stg + krow * 32 + ((krow & 4) << 2), va = stg + 2304 + lane * 32 + ((lane & 4) << 2);
        int b = 0;
#pragma unroll 1
        for (int ci = hw - 3; ci < 16; ci += 3) {
          const uint32_t bo = b ? OFF_F2F - OFF_STG : 0, bn = b ? 0 : OFF_F2F - OFF_STG;
          if (ci + 3 < 16) {
            while (__any_sync(~0u, (uint32_t)clock() - clk0 < HSTART + (ci + 3) * PACE)) __nanosleep(64);
            if (elect_one()) {
              mbar_expect(sbar + 8 * (b ^ 1), 2304 + 2048);
              tma2d(stg + bn, &P.tmK, 16 * cl, 1024 * rank + 64 * (ci + 3) - 8, sbar + 8 * (b ^ 1));
              tma2d(stg + bn + 2304, &P.tmV, 16 * cl, 1024 * rank + 64 * (ci + 3), sbar + 8 * (b ^ 1));
            }
          }
          if (ci >= 0) {
            mbar_wait(sbar + 8 * b, (ph >> b) & 1);
            ph ^= 1 << b;
#pragma unroll 1
            for (int grp = 0; grp < 2; grp++) {
#pragma unroll
              for (int cg = 0; cg < 2; cg++) {
                const uint32_t dst = mapa(xo + (ci >> 3) * 1024 + ((ci & 7) * 4 + 2 * grp) * 16, cg), xbar = mapa(BAR(B_XRAW), cg);
                uint32_t vv[4], kk[4][4];
                ldsm4t(vv, (va ^ (cg * 16)) + bo + grp * 1024);
#pragma unroll
                for (int rg = 0; rg < 4; rg++) ldsm4t(kk[rg], (ka ^ (cg * 16)) + bo + grp * 1024 + rg * 256);
#pragma unroll
                for (int rg = 0; rg < 4; rg++)
                  vv[rg] = hmul(hadd(hadd(hadd(hmul(kk[rg][3], tap[cg][3]), hmul(kk[rg][2], tap[cg][2])), hmul(kk[rg][1], tap[cg][1])), hmul(kk[rg][0], tap[cg][0])), vv[rg]);
#pragma unroll
                for (int rg = 0; rg < 4; rg++) st_async(dst + (rg & 1) * 512 + (rg >> 1) * 16, vv[rg], xbar);
              }
            }
          }
          b ^= 1;
        }
      }
      if (lane == 0) STAMP(3, 3 + hw);
      asm volatile("bar.sync 4, 96;" ::: "memory");
      if (hw == 0 && elect_one()) { mbar_expect(BAR(B_XT), 10240); bulk_ld(sb + OFF_F2F, P.img, 10240, BAR(B_XT)); }
      mbar_wait(BAR(B_XRAW), 0);
#pragma unroll 1
      for (int c = hw; c < 8; c += 3) {
        uint4* p = (uint4*)(smem + OFF_XT + c * XT_STRIDE) + lane;
        uint32_t v[32];
#pragma unroll
        for (int i = 0; i < 8; i++) { const uint4 u = p[i * 32]; v[4 * i] = u.x; v[4 * i + 1] = u.y; v[4 * i + 2] = u.z; v[4 * i + 3] = u.w; }
        const int e = normalise(v, 0.f);
#pragma unroll
        for (int i = 0; i < 8; i++) p[i * 32] = make_uint4(v[4 * i], v[4 * i + 1], v[4 * i + 2], v[4 * i + 3]);
        if (lane == 0) smem[OFF_EX + c] = e;
        if (c < 6 && elect_one()) {
          if (c < 3) mbar_expect(sbar, 4096);
          tma3d(sb + OFF_STG + 2048 * c, &P.tmQ, 16 * cl, 64 * rank, 2 * c, sbar);
        }
      }
      fence_async();
      __syncwarp();
      if (lane == 0) { mbar_arrive(BAR(B_XT)); STAMP(3, 13 + hw); }
      mbar_wait(BAR(B_PKFREE), 0);
      if (hw == 0 && lane == 0) STAMP(3, 19);
      if (PD1) __nanosleep(PD1);
      {
        const int pi = hw < 2 ? 64 * mb + 32 * hw + lane : 512 + 2 * mb + (lane & 1);
        const float* psrc = P.part + hp * 8 * 2176 + 4 * pi;
        uint4 f[8];
#pragma unroll
        for (int p = 0; p < 8; p++) f[p] = ld_rlx4(psrc + p * 2176);
        if (!opaque_true()) __trap();
#pragma unroll 1
        for (int n = 0; __any_sync(~0u, stale8(f, tag) & 1); n++) {
#pragma unroll
          for (int p = 0; p < 8; p++) ld_stale4(f[p], psrc + p * 2176, tag);
          if (n > SPIN_LIMIT) __trap();
        }
        float s0 = 0.f, s1 = 0.f, s2 = 0.f, s3 = 0.f;
#pragma unroll
        for (int p = 0; p < 8; p++) { s0 += __uint_as_float(f[p].x); s1 += __uint_as_float(f[p].y); s2 += __uint_as_float(f[p].z); s3 += __uint_as_float(f[p].w); }
        if (hw < 2 || lane < 2) st_tag4(P.kv + hp * 2176 + (4 * pi), s0, s1, s2, s3, tag);
      }
      if (lane == 0 && hw == 0) STAMP(3, 8);
      if (hw == 2) {
        unsigned* cnt = P.ocnt + (2 * mb + lane) * 32;
#pragma unroll 1
        for (int hh = 0; hh < 2; hh++) {
          mbar_wait(BAR(hh ? B_ODONE1 : B_ODONE), 0);
          if (lane < 2) asm volatile("red.release.gpu.global.add.u32 [%0], 1;" ::"l"(cnt + hh * 512) : "memory");
          if (lane == 0) STAMP(3, hh ? 6 : 7);
        }
        poll_ge(&P.ocnt[512 + rb * 32], 16 * (epoch + 1));
        asm volatile("fence.proxy.async.global;" ::: "memory");
        if (lane == 0) { mbar_arrive(BAR(B_O1RDY)); STAMP(2, 4); }
        __syncwarp();
      } else {
        if (PD2) __nanosleep(PD2);
        const int t = hw * 32 + lane;
        uint4 f[8];
        const float* src = P.kv + hp * 2176 + (4 * t);
        const float* zsrc = P.kv + hp * 2176 + (2048 + (t & 48) + 2 * (lane & 6));
        uint4 zp = ld_rlx4(zsrc);
#pragma unroll
        for (int p = 0; p < 8; p++) f[p] = ld_rlx4(src + 4 * ((p & 3) * 128 + (p >> 2) * 64));
        if (!opaque_true()) __trap();
#pragma unroll 1
        for (int n = 0; __any_sync(~0u, (stale8(f, tag) | (zp.x ^ tag)) & 1); n++) {
          ld_stale4(zp, zsrc, tag);
#pragma unroll
          for (int p = 0; p < 8; p++) ld_stale4(f[p], src + 4 * ((p & 3) * 128 + (p >> 2) * 64), tag);
          if (n > SPIN_LIMIT) __trap();
        }
#define PK2U(a, b) pk2(__uint_as_float(a), __uint_as_float(b))
#pragma unroll
        for (int hh = 0; hh < 2; hh++) {
          const uint4* ff = &f[4 * hh];
          uint8_t* dst = smem + OFF_KVB + hh * 2560 + q * 512 + (16 * hw + g) * 16;
          *(uint4*)dst = make_uint4(PK2U(ff[0].x, ff[0].y), PK2U(ff[1].x, ff[1].y), PK2U(ff[2].x, ff[2].y), PK2U(ff[3].x, ff[3].y));
          *(uint4*)(dst + 128) = make_uint4(PK2U(ff[0].z, ff[0].w), PK2U(ff[1].z, ff[1].w), PK2U(ff[2].z, ff[2].w), PK2U(ff[3].z, ff[3].w));
        }
        const uint32_t zf = (lane & 1) ? ((lane & 8) ? zp.w : zp.z) : ((lane & 8) ? zp.y : zp.x);
        const uint32_t zz = PK2U(zf, zf);
        *(uint4*)(smem + OFF_KVB + hw * 2560 + 2048 + lane * 16) = make_uint4(zz, zz, zz, zz);
        fence_async();
        __syncwarp();
        if (lane == 0) { mbar_arrive(BAR(B_KV)); if (hw == 0) STAMP(3, 9); }
      }
#define QBUF(ci) (sb + 2048 * (ci) + ((ci) < 6 ? OFF_STG : (ci) < 10 ? OFF_SPARE - 6 * 2048 : OFF_F2F - 10 * 2048))
      mbar_wait(BAR(B_Y), 0);
      if (elect_one()) {
        mbar_expect(sbar + 8, 4096);
#pragma unroll 1
        for (int ci = hw ? hw + 9 : 12; ci < 16; ci += 3) tma3d(QBUF(ci), &P.tmQ, 16 * cl, 64 * rank + 32, 2 * (ci & 7), sbar + 8);
      }
      mbar_wait(BAR(B_Q), 0);
      {
        const float2 sc0 = *(const float2*)(smem + OFF_SCALE + 8 * q), sc1 = *(const float2*)(smem + OFF_SCALE + 32 + 8 * q);
        const uint32_t yl = sb + OFF_XT + (lane & 7) * XT_STRIDE + (lane >> 3) * 16;
#pragma unroll 1
        for (int ci = hw; ci < 16; ci += 3) {
          const uint32_t qb = QBUF(ci);
          const int b = ci >= 10;
          mbar_wait(sbar + 8 * b, (ph >> b) & 1);
#pragma unroll 1
          for (int nl = 0; nl < 2; nl++) {
            uint32_t yy[2][4], qq[2][4];
            const uint32_t qa = qb + lane * 32 + ((lane & 4) << 2) + nl * 1024;
#pragma unroll
            for (int cg = 0; cg < 2; cg++) { ldsm4t(yy[cg], yl + cg * 2048 + (2 * ci + nl) * 64); ldsm4(qq[cg], qa ^ (cg * 16)); }
#pragma unroll
            for (int cg = 0; cg < 2; cg++) {
              const float2 sc = cg ? sc1 : sc0;
#pragma unroll
              for (int m = 0; m < 4; m++) {
                const float2 f = __half22float2(*(const __half2*)&yy[cg][m]);
                qq[cg][m] = hmul(qq[cg][m], pk2(f.x * sc.x, f.y * sc.y));
              }
              stsm4(qa ^ (cg * 16), qq[cg][0], qq[cg][1], qq[cg][2], qq[cg][3]);
            }
          }
          fence_async();
          __syncwarp();
          if (elect_one()) tma3d_st(&P.tmOA, qb, 16 * cl, 64 * rank + 32 * (ci >> 3), 2 * (ci & 7));
        }
        asm volatile("cp.async.bulk.commit_group;\ncp.async.bulk.wait_group.read 0;" ::: "memory");
      }
      if (lane == 0) STAMP(3, 10 + hw);
    }
  }
}

typedef CUresult (*EncodeFn)(CUtensorMap*, CUtensorMapDataType, cuuint32_t, void*, const cuuint64_t*, const cuuint64_t*,
                             const cuuint32_t*, const cuuint32_t*, CUtensorMapInterleave, CUtensorMapSwizzle,
                             CUtensorMapL2promotion, CUtensorMapFloatOOBfill);

static void enc(EncodeFn fn, CUtensorMap* m, const void* p, int rank, const cuuint64_t* dims, const cuuint64_t* strides,
                const cuuint32_t* box, CUtensorMapSwizzle swz, CUtensorMapL2promotion promo) {
  cuuint32_t es[4] = {1, 1, 1, 1};
  fn(m, CU_TENSOR_MAP_DATA_TYPE_BFLOAT16, rank, (void*)p, dims, strides, box, es, CU_TENSOR_MAP_INTERLEAVE_NONE, swz, promo,
     CU_TENSOR_MAP_FLOAT_OOB_FILL_NONE);
}

extern "C" void kernel_launch(void* const* d_in, const int* in_sizes, int n_in, void* d_out, int out_size) {
  void* fp = nullptr;
  cudaDriverEntryPointQueryResult qr;
  cudaGetDriverEntryPoint("cuTensorMapEncodeTiled", &fp, cudaEnableDefault, &qr);
  EncodeFn fn = (EncodeFn)fp;
  Params P;
  P.shift_k = (const __nv_bfloat16*)d_in[3]; P.h = (const __nv_bfloat16*)d_in[4]; P.D = (const __nv_bfloat16*)d_in[5];
  P.q = (const __nv_bfloat16*)d_in[0];
  cudaGetSymbolAddress((void**)&P.part, g_part); cudaGetSymbolAddress((void**)&P.kv, g_kv); cudaGetSymbolAddress((void**)&P.o, g_o);
  cudaGetSymbolAddress((void**)&P.ocnt, g_ocnt); cudaGetSymbolAddress((void**)&P.epoch, g_epoch);
  cudaGetSymbolAddress((void**)&P.thr, c_thr); cudaGetSymbolAddress((void**)&P.img, c_img);
  P.x = (const __nv_bfloat16*)d_in[6]; P.w = (const __nv_bfloat16*)d_in[7]; P.wo = (const __nv_bfloat16*)d_in[8];
  const CUtensorMapSwizzle S128 = CU_TENSOR_MAP_SWIZZLE_128B, S32 = CU_TENSOR_MAP_SWIZZLE_32B;
  const CUtensorMapL2promotion P0 = CU_TENSOR_MAP_L2_PROMOTION_NONE, P128 = CU_TENSOR_MAP_L2_PROMOTION_L2_128B;
  { cuuint64_t d[2] = {1024, 2048}, s[1] = {2048}; cuuint32_t b[2] = {64, 128}; enc(fn, &P.tmX, d_in[6], 2, d, s, b, S128, P128); }
  { cuuint64_t d[3] = {1024, 1024, 3}, s[2] = {6144, 2048}; cuuint32_t b[3] = {64, 64, 3}; enc(fn, &P.tmW, d_in[7], 3, d, s, b, S128, P128); }
  { cuuint64_t d[4] = {64, 64, 16, 16}, s[3] = {2048, 131072, 128}; cuuint32_t b[4] = {64, 32, 2, 2}; enc(fn, &P.tmWo, d_in[8], 4, d, s, b, S128, P128); }
  { cuuint64_t d[4] = {64, 64, 16, 16}, s[3] = {2048, 131072, 128}; cuuint32_t b[4] = {64, 32, 2, 1}; enc(fn, &P.tmWo1, d_in[8], 4, d, s, b, S128, P128); }
  { cuuint64_t d[2] = {1024, 2048}, s[1] = {2048}; cuuint32_t b[2] = {16, 72}; enc(fn, &P.tmK, d_in[1], 2, d, s, b, S32, PKV); }
  { cuuint64_t d[2] = {1024, 2048}, s[1] = {2048}; cuuint32_t b[2] = {16, 64}; enc(fn, &P.tmV, d_in[2], 2, d, s, b, S32, PKV); }
  { cuuint64_t d[3] = {1024, 128, 16}, s[2] = {32768, 2048}; cuuint32_t b[3] = {16, 32, 2}; enc(fn, &P.tmQ, d_in[0], 3, d, s, b, S32, PKV); }
  { cuuint64_t d[3] = {1024, 128, 16}, s[2] = {65536, 4096}; cuuint32_t b[3] = {16, 32, 2}; enc(fn, &P.tmOA, d_out, 3, d, s, b, S32, P0); }
  { cuuint64_t d[2] = {2048, 2048}, s[1] = {4096}; cuuint32_t b[2] = {64, 64}; enc(fn, &P.tmOB, d_out, 2, d, s, b, S128, P0); }
  cudaFuncSetAttribute(fused_kernel, cudaFuncAttributeMaxDynamicSharedMemorySize, SMEM_TOTAL);
  fused_kernel<<<128, 384, SMEM_TOTAL>>>(P);
}
```

```cpp
#include <cuda_runtime.h>
#include <cuda_bf16.h>
#include <cuda_fp16.h>
#include <cuda.h>
#include <stdint.h>

template<int TA, int TB, int SA=1> __device__ __forceinline__ void wgmma_ss_n192(float (&d)[96], uint64_t da, uint64_t db, int scale_d) {
  asm volatile("{\n.reg .pred p;\nsetp.ne.b32 p, %98, 0;\n"
    "wgmma.mma_async.sync.aligned.m64n192k16.f32.bf16.bf16 {%0, %1, %2, %3, %4, %5, %6, %7, %8, %9, %10, %11, %12, %13, %14, %15, %16, %17, %18, %19, %20, %21, %22, %23, %24, %25, %26, %27, %28, %29, %30, %31, %32, %33, %34, %35, %36, %37, %38, %39, %40, %41, %42, %43, %44, %45, %46, %47, %48, %49, %50, %51, %52, %53, %54, %55, %56, %57, %58, %59, %60, %61, %62, %63, %64, %65, %66, %67, %68, %69, %70, %71, %72, %73, %74, %75, %76, %77, %78, %79, %80, %81, %82, %83, %84, %85, %86, %87, %88, %89, %90, %91, %92, %93, %94, %95}, %96, %97, p, %101, 1, %99, %100;\n}\n"
    : "+f"(d[0]), "+f"(d[1]), "+f"(d[2]), "+f"(d[3]), "+f"(d[4]), "+f"(d[5]), "+f"(d[6]), "+f"(d[7]), "+f"(d[8]), "+f"(d[9]), "+f"(d[10]), "+f"(d[11]), "+f"(d[12]), "+f"(d[13]), "+f"(d[14]), "+f"(d[15]), "+f"(d[16]), "+f"(d[17]), "+f"(d[18]), "+f"(d[19]), "+f"(d[20]), "+f"(d[21]), "+f"(d[22]), "+f"(d[23]), "+f"(d[24]), "+f"(d[25]), "+f"(d[26]), "+f"(d[27]), "+f"(d[28]), "+f"(d[29]), "+f"(d[30]), "+f"(d[31]), "+f"(d[32]), "+f"(d[33]), "+f"(d[34]), "+f"(d[35]), "+f"(d[36]), "+f"(d[37]), "+f"(d[38]), "+f"(d[39]), "+f"(d[40]), "+f"(d[41]), "+f"(d[42]), "+f"(d[43]), "+f"(d[44]), "+f"(d[45]), "+f"(d[46]), "+f"(d[47]), "+f"(d[48]), "+f"(d[49]), "+f"(d[50]), "+f"(d[51]), "+f"(d[52]), "+f"(d[53]), "+f"(d[54]), "+f"(d[55]), "+f"(d[56]), "+f"(d[57]), "+f"(d[58]), "+f"(d[59]), "+f"(d[60]), "+f"(d[61]), "+f"(d[62]), "+f"(d[63]), "+f"(d[64]), "+f"(d[65]), "+f"(d[66]), "+f"(d[67]), "+f"(d[68]), "+f"(d[69]), "+f"(d[70]), "+f"(d[71]), "+f"(d[72]), "+f"(d[73]), "+f"(d[74]), "+f"(d[75]), "+f"(d[76]), "+f"(d[77]), "+f"(d[78]), "+f"(d[79]), "+f"(d[80]), "+f"(d[81]), "+f"(d[82]), "+f"(d[83]), "+f"(d[84]), "+f"(d[85]), "+f"(d[86]), "+f"(d[87]), "+f"(d[88]), "+f"(d[89]), "+f"(d[90]), "+f"(d[91]), "+f"(d[92]), "+f"(d[93]), "+f"(d[94]), "+f"(d[95])
    : "l"(da), "l"(db), "r"(scale_d), "n"(TA), "n"(TB), "n"(SA));
}
template<int TA, int TB, int SA=1> __device__ __forceinline__ void wgmma_ss_n128(float (&d)[64], uint64_t da, uint64_t db, int scale_d) {
  asm volatile("{\n.reg .pred p;\nsetp.ne.b32 p, %66, 0;\n"
    "wgmma.mma_async.sync.aligned.m64n128k16.f32.bf16.bf16 {%0, %1, %2, %3, %4, %5, %6, %7, %8, %9, %10, %11, %12, %13, %14, %15, %16, %17, %18, %19, %20, %21, %22, %23, %24, %25, %26, %27, %28, %29, %30, %31, %32, %33, %34, %35, %36, %37, %38, %39, %40, %41, %42, %43, %44, %45, %46, %47, %48, %49, %50, %51, %52, %53, %54, %55, %56, %57, %58, %59, %60, %61, %62, %63}, %64, %65, p, %69, 1, %67, %68;\n}\n"
    : "+f"(d[0]), "+f"(d[1]), "+f"(d[2]), "+f"(d[3]), "+f"(d[4]), "+f"(d[5]), "+f"(d[6]), "+f"(d[7]), "+f"(d[8]), "+f"(d[9]), "+f"(d[10]), "+f"(d[11]), "+f"(d[12]), "+f"(d[13]), "+f"(d[14]), "+f"(d[15]), "+f"(d[16]), "+f"(d[17]), "+f"(d[18]), "+f"(d[19]), "+f"(d[20]), "+f"(d[21]), "+f"(d[22]), "+f"(d[23]), "+f"(d[24]), "+f"(d[25]), "+f"(d[26]), "+f"(d[27]), "+f"(d[28]), "+f"(d[29]), "+f"(d[30]), "+f"(d[31]), "+f"(d[32]), "+f"(d[33]), "+f"(d[34]), "+f"(d[35]), "+f"(d[36]), "+f"(d[37]), "+f"(d[38]), "+f"(d[39]), "+f"(d[40]), "+f"(d[41]), "+f"(d[42]), "+f"(d[43]), "+f"(d[44]), "+f"(d[45]), "+f"(d[46]), "+f"(d[47]), "+f"(d[48]), "+f"(d[49]), "+f"(d[50]), "+f"(d[51]), "+f"(d[52]), "+f"(d[53]), "+f"(d[54]), "+f"(d[55]), "+f"(d[56]), "+f"(d[57]), "+f"(d[58]), "+f"(d[59]), "+f"(d[60]), "+f"(d[61]), "+f"(d[62]), "+f"(d[63])
    : "l"(da), "l"(db), "r"(scale_d), "n"(TA), "n"(TB), "n"(SA));
}
template<int TA, int TB, int SA=1> __device__ __forceinline__ void wgmma_ss_n72(float (&d)[36], uint64_t da, uint64_t db, int scale_d) {
  asm volatile("{\n.reg .pred p;\nsetp.ne.b32 p, %38, 0;\n"
    "wgmma.mma_async.sync.aligned.m64n72k16.f32.bf16.bf16 {%0, %1, %2, %3, %4, %5, %6, %7, %8, %9, %10, %11, %12, %13, %14, %15, %16, %17, %18, %19, %20, %21, %22, %23, %24, %25, %26, %27, %28, %29, %30, %31, %32, %33, %34, %35}, %36, %37, p, %41, 1, %39, %40;\n}\n"
    : "+f"(d[0]), "+f"(d[1]), "+f"(d[2]), "+f"(d[3]), "+f"(d[4]), "+f"(d[5]), "+f"(d[6]), "+f"(d[7]), "+f"(d[8]), "+f"(d[9]), "+f"(d[10]), "+f"(d[11]), "+f"(d[12]), "+f"(d[13]), "+f"(d[14]), "+f"(d[15]), "+f"(d[16]), "+f"(d[17]), "+f"(d[18]), "+f"(d[19]), "+f"(d[20]), "+f"(d[21]), "+f"(d[22]), "+f"(d[23]), "+f"(d[24]), "+f"(d[25]), "+f"(d[26]), "+f"(d[27]), "+f"(d[28]), "+f"(d[29]), "+f"(d[30]), "+f"(d[31]), "+f"(d[32]), "+f"(d[33]), "+f"(d[34]), "+f"(d[35])
    : "l"(da), "l"(db), "r"(scale_d), "n"(TA), "n"(TB), "n"(SA));
}
template<int TB, int SA=1> __device__ __forceinline__ void wgmma_rs_n40(float (&d)[20], uint32_t a0, uint32_t a1, uint32_t a2, uint32_t a3, uint64_t db, int scale_d) {
  asm volatile("{\n.reg .pred p;\nsetp.ne.b32 p, %25, 0;\n"
    "wgmma.mma_async.sync.aligned.m64n40k16.f32.bf16.bf16 {%0, %1, %2, %3, %4, %5, %6, %7, %8, %9, %10, %11, %12, %13, %14, %15, %16, %17, %18, %19}, {%20, %21, %22, %23}, %24, p, %27, 1, %26;\n}\n"
    : "+f"(d[0]), "+f"(d[1]), "+f"(d[2]), "+f"(d[3]), "+f"(d[4]), "+f"(d[5]), "+f"(d[6]), "+f"(d[7]), "+f"(d[8]), "+f"(d[9]), "+f"(d[10]), "+f"(d[11]), "+f"(d[12]), "+f"(d[13]), "+f"(d[14]), "+f"(d[15]), "+f"(d[16]), "+f"(d[17]), "+f"(d[18]), "+f"(d[19])
    : "r"(a0), "r"(a1), "r"(a2), "r"(a3), "l"(db), "r"(scale_d), "n"(TB), "n"(SA));
}
template<int TB> __device__ __forceinline__ void wgmma_hrs_n64(uint32_t (&d)[16], uint32_t a0, uint32_t a1, uint32_t a2, uint32_t a3, uint64_t db, int scale_d) {
  asm volatile("{\n.reg .pred p;\nsetp.ne.b32 p, %21, 0;\n"
    "wgmma.mma_async.sync.aligned.m64n64k16.f16.f16.f16 {%0, %1, %2, %3, %4, %5, %6, %7, %8, %9, %10, %11, %12, %13, %14, %15}, {%16, %17, %18, %19}, %20, p, 1, 1, %22;\n}\n"
    : "+r"(d[0]), "+r"(d[1]), "+r"(d[2]), "+r"(d[3]), "+r"(d[4]), "+r"(d[5]), "+r"(d[6]), "+r"(d[7]), "+r"(d[8]), "+r"(d[9]), "+r"(d[10]), "+r"(d[11]), "+r"(d[12]), "+r"(d[13]), "+r"(d[14]), "+r"(d[15])
    : "r"(a0), "r"(a1), "r"(a2), "r"(a3), "l"(db), "r"(scale_d), "n"(TB));
}
template<int TB> __device__ __forceinline__ void wgmma_hrs_n32(uint32_t (&d)[8], uint32_t a0, uint32_t a1, uint32_t a2, uint32_t a3, uint64_t db, int scale_d) {
  asm volatile("{\n.reg .pred p;\nsetp.ne.b32 p, %13, 0;\n"
    "wgmma.mma_async.sync.aligned.m64n32k16.f16.f16.f16 {%0, %1, %2, %3, %4, %5, %6, %7}, {%8, %9, %10, %11}, %12, p, 1, 1, %14;\n}\n"
    : "+r"(d[0]), "+r"(d[1]), "+r"(d[2]), "+r"(d[3]), "+r"(d[4]), "+r"(d[5]), "+r"(d[6]), "+r"(d[7])
    : "r"(a0), "r"(a1), "r"(a2), "r"(a3), "l"(db), "r"(scale_d), "n"(TB));
}

__device__ __align__(128) const uint32_t c_thr[1536] = {
  0x33fb33ff,0xa49c9de4,0x33273352,0xaf2cae76,0x33e233f1,0xa96ca7bd,0x32c432f7,0xb045afdd,0x33b733cf,0xac3eaaf7,0x3250328c,0xb0eab099,
  0x3378339a,0xadbcacff,0x31cd3211,0xb182b137,0x33d033fb,0xaadea46a,0x299e2d17,0xb3e0b396,0x32fb337a,0xafd2adb1,0xa78b1f76,0xb3f2b3ff,
  0x318b3254,0xb1c5b0e5,0xae6bac32,0xb354b3b8,0x2f4230a3,0xb321b285,0xb133b040,0xb215b2c7,0x337c33f2,0xada5a759,0xb179afc8,0xb1d6b2fe,
  0x31463293,0xb204b08e,0xb394b2ba,0xad23b055,0x2b402f4e,0xb3cbb31e,0xb3e4b3f9,0x293ba533,0xac269c52,0xb3bab400,0xb258b357,0x30e02e5f,
  0x330133e5,0xafbda922,0xb3f3b3c9,0x2727ab59,0x2deb314a,0xb36fb200,0xb194b32f,0x31bc2f0a,0xacdb2084,0xb39fb3ff,0xa565aea4,0x33f93347,
  0xb2b6b0db,0xb05ab25c,0x30892c1a,0x329733bc,0x326033d4,0xb0d6aa94,0xb00ab29b,0x32e83084,0x20e82f64,0xb3feb318,0x2d8da597,0x338133f8,
  0xb1fcae48,0xb14fb35c,0x339031b8,0x2d3a3199,0xb3e6b3ae,0x2909ac7b,0x32d133f4,0xb030a6f5,0x319d33bf,0xb1b3ac02,0x2e3ca874,0x335e33ec,
  0xacc32b89,0xb3a3b3c6,0x33f83276,0x25c930b7,0xb3dcb1f8,0xaa01b154,0x30653335,0xb2b0aef4,0xb107b383,0x32392d81,0xafa6214d,0xb307b3fe,
  0x30bc33a5,0xb273acb7,0x33c5311b,0x2ba23229,0xb0cc94b6,0xb267b400,0x30153360,0xb2e1ae31,0xb385b3ab,0x2d76ac93,0xb166a691,0xb1e7b3f5,
  0x22deb06a,0x33fd32ac,0xb337b3da,0x2ee8aa19,0x2f853387,0xb310ad6a,0x322d33fe,0xb1162216,0xb2a9abd3,0xb06fb3c2,0xb07428a6,0xb2a5b3ea,
  0xb111b3e9,0x323128be,0xb30db3c3,0x2f90abba,0x31aa227a,0x31a633fd,0x2e25ad5e,0x33633389,0x2d6a3365,0xb387ae1a,0xa21631aa,0xb3feb1a6,
  0xb3c2af85,0xabd3b310,0xb3eab22d,0x28a6b116,0xa8beb2a9,0x33e9306f,0x2bbab074,0x33c332a5,0x33fd3111,0x227a3231,0x3389330d,0xad5e2f90,
  0x2a63333f,0xb3d7aec6,0xb2a2a1b1,0xb07ab3fe,0xb3f7b158,0x25fbb1f4,0xacb7b38b,0x33a52d52,0x2e0eb025,0x336832d8,0x340030bc,0x14b63273,
  0x323533c0,0xb10c2beb,0xac9330cc,0xb3abb267,0x23433316,0xb3fdaf6f,0xb38eb225,0x2d46b11f,0xb342b29e,0x2ebbb07f,0x31e3aa7c,0x316b33d6,
  0x3264a6c3,0x30d133f5,0x2c0233ac,0xb3bfac87,0x28f0336a,0xb3e7ae02,0xb3c6b19d,0x2b89b1b3,0xa59732e8,0xb3f8b00a,0xaccfb3ed,0x33a1285b,
  0xb1b8b381,0x3199ad8d,0x336c31df,0xadf73170,0x33f42d3a,0x26f53390,0xb30423a7,0xafb2b3fc,0xb05f3030,0xb2b3b2d1,0x29e8b27a,0x33dd30b2,
  0xab5932b6,0xb3c9b05a,0x30adb089,0x327e3297,0xaf0ab3f3,0x332fa727,0x240633b0,0xb3fcac6f,0x33473194,0xaea431bc,0xb174b359,0x31daae54,
  0xb3bca565,0xac1ab3f9,0x33ee2f59,0xa842331b,0xaddf3281,0xb371b0a8,0x34002b40,0x1c5233cb,0xa759b3ef,0x33f22829,0xb2fe2c26,0xafc8b3ba,
  0x308e337c,0xb2932da5,0x3055b179,0x32ba31d6,0xb31eb146,0x2f4eb204,0xa5333394,0xb3f9ad23,0xaff33249,0xb2f1b0f3,0x30e532fb,0xb2542fd2,
  0x2b28b373,0x33cc2dd4,0xb285b18b,0x30a3b1c5,0x246a33fa,0xb3fba500,0x33962f42,0xad173321,0xadb1b3d0,0x337aaade,0xb3ffa99e,0x1f76b3e0,
  0xb0ee320d,0xb24db13c,0xac4b3398,0xb3b5ad0b,0x304ab289,0x32c1309e,0x2985b3ce,0x33e12b0f,0xaf3732f4,0xb324afe8,0xa4ce33f0,0xb3faa7ef,
  0x2dc8b34f,0x33762e82,0x9de4b3ff,0x33ff1ead,0xb1c931cd,0xb186b182,0xb3762e82,0xadc8b34f,0x324db13c,0x30ee320d,0x33b5ad0b,0x2c4b3398,
  0xb2c1309e,0xb04ab289,0xb3e12b0f,0xa985b3ce,0x3324afe8,0x2f3732f4,0x33faa7ef,0x24ce33f0,0xb285318b,0xb0a3b1c5,0xb2c7ae6b,0x3040b354,
  0x3396af42,0x2d173321,0x31413133,0xb2093215,0xb3ff299e,0x9f76b3e0,0xae8db2bd,0x334cb050,0x33b8278b,0xac3233f2,0x281033b3,0xb3ef2c57,
  0xb31e3146,0xaf4eb204,0xa533b394,0x33f9ad23,0x3400ab40,0x9c5233cb,0xae5f33e4,0xb357a93b,0xb2feac26,0x2fc8b3ba,0x3245b258,0x30f830e0,
  0x30553179,0xb2ba31d6,0xb3df2e99,0xa9b6b34a,0xb39230fd,0xad2fb241,0x3200b301,0x314a2fbd,0x337f1b11,0xad993400,0xb3ff2deb,0xa084b36f,
  0xb005b129,0x32ebb21d,0x325c2cdb,0xb0db339f,0xa92233de,0xb3e529cf,0xab59b2b6,0x33c9b05a,0xb3dd30b2,0xa9e8b27a,0x33d4ab71,0xaa9433c8,
  0x32212c0e,0xb12433bd,0xaf64b0d6,0x3318b260,0x197fb345,0x3400aeaf,0xae4833fe,0xb35c20e8,0xb23d3332,0xb102aeff,0x33aeb14f,0x2c7b31fc,
  0xb3fe3065,0xa14db2b0,0x2ebb307f,0xb342329e,0x300f2fa6,0xb2e53307,0x30d1b3f5,0x326426c3,0x302ab400,0x32d517db,0xb3e72e02,0x28f0b36a,
  0xb3fd2f6f,0x2343b316,0x2d46311f,0xb38e3225,0xb3f53015,0x2691b2e1,0xaf9b33eb,0xb30a288d,0x2a193166,0xb3da31e7,0x33d7aec6,0xaa63333f,
  0x3313b337,0x2f7a2ee8,0xa5fbb1f4,0x33f7b158,0xb1a1a8d7,0x31afb3e8,0xb36832d8,0xae0eb025,0xb3c22f85,0x2bd3b310,0xb3ea322d,0xa8a6b116,
  0xa8be32a9,0xb3e9306f,0x2bba3074,0xb3c332a5,0x33fdb111,0xa27a3231,0x3389b30d,0x2d5e2f90,0xa216b1aa,0x33feb1a6,0xaed2ae25,0x333db363,
  0xb3652edd,0x2e1ab33a,0xb1aa227a,0x31a6b3fd,0xaf853387,0xb3102d6a,0xb22d33fe,0xb116a216,0x32a9abd3,0xb06f33c2,0x307428a6,0xb2a533ea,
  0x3111b3e9,0x3231a8be,0x330db3c3,0x2f902bba,0xb2e12e31,0x3015b360,0x288db1a1,0x33ebb1af,0xb1e733f5,0xb1662691,0xb33f2f9b,0x2ec6b30a,
  0x2ee82a19,0xb33733da,0xb15833d7,0xb1f42a63,0x33e8b313,0x28d72f7a,0x302525fb,0xb2d833f7,0xb2392d81,0x3107b383,0x3307b3fe,0x2fa6214d,
  0xb35e33ec,0xae3ca874,0x97dbb00f,0x3400b2e5,0xa5c930b7,0xb3f83276,0xb316302a,0x2f6fb2d5,0x32b0aef4,0xb0653335,0xb29e33fd,0xb07f2343,
  0xb1702ccf,0x31dfb3a1,0x3345b124,0xaeaf3221,0xb3fc336c,0xa3a7adf7,0x3332b400,0x2eff997f,0xb0b23304,0xb27a2fb2,0x2b71b102,0x33c8b23d,
  0x2c0e29e8,0xb3bd33dd,0xb0d62a94,0x3260b3d4,0xb0892c1a,0x3297b3bc,0x2aad2842,0xb3d333ee,0xb3b0327e,0x2c6fb0ad,0x3241b035,0xb0fd32ce,
  0xb35933fc,0xae542406,0x3400b392,0x1b112d2f,0xaf5931da,0xb31b3174,0x321db37f,0x3129ad99,0xaf152ac6,0x332cb3d2,0xb1463293,0xb204308e,
  0xb281312e,0x30a8b219,0xab402f4e,0xb3cb331e,0xb3ef3371,0x2829addf,0x2c269c52,0xb3ba3400,0xb37c33f2,0xada52759,0x3179afc8,0xb1d632fe,
  0xacf32953,0x339cb3e3,0xb3fa33cc,0x2500ab28,0xb0942f21,0x3290b32a,0xb3d033fb,0xaade246a,0xb249317d,0x30f3b1d2,0xb2fb337a,0xafd22db1,
  0xb37332f1,0x2dd4aff3,0xb18b3254,0xb1c530e5,0xa96c27bd,0x33e2b3f1,0xb0452fdd,0x32c4b2f7,0xac3e2af7,0x33b7b3cf,0xb0ea3099,0x3250b28c,
  0xadbc2cff,0x3378b39a,0xb1823137,0x31cdb211,0xaf2c2e76,0x3327b352,0xb20d31c9,0x313cb186,0x313c3186,0xb20db1c9,0x2d0b2dc8,0xb398b376,
  0x309e30ee,0xb289b24d,0x2b0f2c4b,0xb3ceb3b5,0x2fe8304a,0xb2f4b2c1,0x27ef2985,0xb3f0b3e1,0x2e822f37,0xb34fb324,0x1ead24ce,0xb3ffb3fa,
  0xb2bdb209,0xb050b141,0xb290b32a,0x30942f21,0xb3b3b34c,0xac57ae8d,0xb0f3b1d2,0x3249317d,0xb400b3ef,0x1d1ba810,0xadd4aff3,0x337332f1,
  0xb39cb3e3,0x2cf32953,0xa500ab28,0x33fa33cc,0xae99b0f8,0x334a3245,0x33ff33b2,0x201f2c63,0x2438a9b6,0x33fc33df,0x332c33d2,0xaf15aac6,
  0x303a2ce7,0x32cb339e,0x30a83219,0xb281b12e,0x32ee31c0,0x2ffe3190,0x28292ddf,0xb3efb371,0x33b0327e,0x2c6f30ad,0xb241b035,0xb0fdb2ce,
  0x335933fc,0xae54a406,0xb400b392,0x1b11ad2f,0x2f5931da,0xb31bb174,0xb21db37f,0x31292d99,0xaaad2842,0xb3d3b3ee,0xa9cfb005,0x33de32eb,
  0x285b305f,0xb3edb2b3,0x2c0ea9e8,0x33bd33dd,0xb170accf,0xb1dfb3a1,0x33453124,0x2eaf3221,0xb3fcb36c,0x23a7adf7,0x33323400,0xaeff997f,
  0xb0b2b304,0x327a2fb2,0x2b713102,0xb3c8b23d,0xb400b2e5,0x17dbb00f,0x2e023264,0xb36ab0d1,0xaf6fb2d5,0x3316302a,0xb11fa8f0,0xb225b3e7,
  0x307f2343,0x329e33fd,0xb3d6b38e,0x2a7cad46,0x33f53342,0xa6c32ebb,0xac87b1e3,0x33ac316b,0x28d7af7a,0x33e83313,0xb2d8b3f7,0x3025a5fb,
  0x33eb31af,0x288d31a1,0x2bebae0e,0x33c03368,0x2ec6330a,0xb33faf9b,0x33fe3235,0x21b1310c,0xb1f4aa63,0xb158b3d7,0x2d5232a2,0xb38bb07a,
  0x33a7333d,0xacab2ed2,0x33f63162,0x262d31eb,0xaa4b301a,0xb3d8b2de,0x2a32326b,0xb3d9b0c7,0xb3f6b26f,0x265fb0c1,0xb3a9b020,0xac9fb2db,
  0x0e48b15d,0x340031f0,0xae1ab33a,0x33652edd,0xaed22e25,0xb33db363,0xb1eb0e48,0xb162b400,0xb2deb3a7,0x301aacab,0xb0c7b3f6,0x326b262d,
  0x30c1aa4b,0x326f33d8,0x32db2a32,0x302033d9,0x31f033f6,0xb15d265f,0x2edd33a9,0xb33aac9f,0xb2acb385,0x306aad76,0x2a19b166,0x33da31e7,
  0x3229a2de,0x311b33fd,0x33133337,0xaf7a2ee8,0x2e3133c5,0xb360aba2,0xb1a128d7,0xb1afb3e8,0xb3f5b015,0xa691b2e1,0xaf9bb3eb,0x330a288d,
  0x3154acc3,0x31f833a3,0x2ef433f8,0xb335a5c9,0x2d8133dc,0xb383aa01,0xb3feb065,0x214db2b0,0xb3ecb107,0x2874b239,0x300fafa6,0x32e53307,
  0x30b7ae3c,0x3276335e,0x302a3400,0xb2d517db,0x312433bd,0xb2212c0e,0xb318b260,0x2f64b0d6,0xb400aeaf,0x997fb345,0x335c20e8,0x2e4833fe,
  0x3102aeff,0x323d3332,0xac7b31fc,0xb3aeb14f,0x2a9433c8,0xb3d4ab71,0xb084b3e6,0x329ba909,0xb2ce2aad,0xb035b3d3,0x33e529cf,0x292233de,
  0x2d2fb241,0x339230fd,0xb14a2fbd,0xb200b301,0x2d993400,0xb37f1b11,0x2084b36f,0x33ff2deb,0xb2ebb21d,0x3005b129,0x30db339f,0xb25c2cdb,
  0xae5fb3e4,0x3357a93b,0xb190303a,0xb1c0b2cb,0x32453258,0xb0f830e0,0x2c63b2ee,0x33b22ffe,0xb3dfae99,0x29b6b34a,0x2ac633ff,0xb3d2a01f,
  0x339ea438,0x2ce733fc,0xb12eb32c,0x3219af15,0x33b8a78b,0x2c3233f2,0x2810b3b3,0x33ef2c57,0xb2c72e6b,0xb040b354,0x29533400,0xb3e31d1b,
  0x3141b133,0x32093215,0xaf21b39c,0x332aacf3,0xae8d32bd,0xb34cb050,0x317d3290,0xb1d23094,0x27bd33fb,0xb3f1249c,0x2fdd3327,0xb2f72f2c,
  0xaaf7b3e2,0x33cfa96c,0xb099b2c4,0x328cb045,0x2cff33b7,0xb39a2c3e,0x31373250,0xb21130ea,0xae76b378,0x3352adbc,0xb1c9b1cd,0x3186b182,
  0xb3ff1ead,0x1de4b3ff,0xb352adbc,0x2e76b378,0x33f1249c,0xa7bd33fb,0x32f72f2c,0xafdd3327,0xb3cfa96c,0x2af7b3e2,0xb28cb045,0x3099b2c4,
  0x339a2c3e,0xacff33b7,0x321130ea,0xb1373250,0x2953b400,0x33e31d1b,0x33ccadd4,0x2b283373,0xaf21339c,0xb32aacf3,0xb3fb2500,0x246ab3fa,
  0x317db290,0x31d23094,0x337a2ade,0xadb133d0,0xb2f130f3,0xaff3b249,0xb254afd2,0x30e5b2fb,0x339e2438,0xace733fc,0xb12e332c,0xb219af15,
  0xb190b03a,0x31c0b2cb,0x3371b0a8,0x2ddf3281,0x2c6332ee,0xb3b22ffe,0xb3f22829,0x2759b3ef,0x2ac6b3ff,0x33d2a01f,0x32932da5,0xb08e337c,
  0xaf0a33f3,0xb32fa727,0x2406b3b0,0x33fcac6f,0x3347b194,0x2ea431bc,0xb1743359,0xb1daae54,0xb3bc2565,0x2c1ab3f9,0x33eeaf59,0x2842331b,
  0x30ad3089,0xb27e3297,0xb2ceaaad,0x3035b3d3,0xb29ba909,0x3084b3e6,0x305f3030,0xb2b332d1,0x259732e8,0xb3f8300a,0x2ccfb3ed,0x33a1a85b,
  0x31b8b381,0x31992d8d,0xb36c31df,0xadf7b170,0xb3f42d3a,0x26f5b390,0x330423a7,0xafb233fc,0x316bb3d6,0x31e32a7c,0xb3832a01,0x2d81b3dc,
  0xb3bf2c87,0x2c02b3ac,0x28743239,0xb3ec3107,0x2b8931b3,0xb3c6319d,0x3276b35e,0x30b72e3c,0x31f8b3a3,0x31542cc3,0xb33525c9,0x2ef4b3f8,
  0x310c2beb,0xb23533c0,0x33abb267,0x2c9330cc,0x307ab3fe,0x32a2a1b1,0xb06aad76,0x32acb385,0xb3a52d52,0x2cb7b38b,0xb11b33fd,0xb229a2de,
  0x94b63273,0xb40030bc,0x3360aba2,0xae3133c5,0xb2de33a7,0xb01aacab,0xb0c733f6,0xb26b262d,0x30c12a4b,0xb26f33d8,0x32dbaa32,0xb02033d9,
  0x31f0b3f6,0x315d265f,0x2eddb3a9,0x333aac9f,0xb1eb8e48,0x3162b400,0xb3872e1a,0x2d6ab365,0xae25ad5e,0x3363b389,0x8e48b15d,0x3400b1f0,
  0xb3a7333d,0xacabaed2,0xb3f63162,0x262db1eb,0x2a4b301a,0xb3d832de,0xaa32326b,0xb3d930c7,0x33f6b26f,0x265f30c1,0x33a9b020,0xac9f32db,
  0x33c0b368,0x2beb2e0e,0x30cc94b6,0xb2673400,0x21b1b10c,0x33feb235,0x3385b3ab,0x2d762c93,0xb38b307a,0x2d52b2a2,0xa2deb06a,0x33fdb2ac,
  0xb0bc33a5,0xb2732cb7,0xb3c5311b,0x2ba2b229,0x26c32ebb,0xb3f53342,0xb3ac316b,0x2c87b1e3,0x336ab0d1,0xae023264,0xb19d33bf,0xb1b32c02,
  0x3225b3e7,0x311fa8f0,0x2cc32b89,0xb3a333c6,0xaa7cad46,0x33d6b38e,0x33dcb1f8,0xaa013154,0xb3fe3318,0x20e8af64,0x3381b3f8,0x2d8d2597,
  0xb14f335c,0xb1fc2e48,0x2d3ab199,0x3390b1b8,0x29092c7b,0xb3e633ae,0xb03026f5,0x32d1b3f4,0x32e8b084,0xb00a329b,0xb3ed32b3,0x285bb05f,
  0x29cfb005,0x33deb2eb,0xb05a325c,0xb2b630db,0xafbd2922,0x3301b3e5,0x27272b59,0xb3f333c9,0xb36f3200,0x2debb14a,0x31bcaf0a,0xb194332f,
  0xb39f33ff,0xacdba084,0x33f9b347,0xa5652ea4,0x3394b2ba,0xad233055,0xa438a9b6,0x33fcb3df,0x33e4b3f9,0x293b2533,0xb03a2ce7,0x32cbb39e,
  0x3258b357,0x30e0ae5f,0xb2ee31c0,0x2ffeb190,0x2e99b0f8,0x334ab245,0xb3ff33b2,0x201fac63,0xaf4230a3,0xb3213285,0x3133b040,0xb21532c7,
  0xa99e2d17,0xb3e03396,0x32bdb209,0xb0503141,0x278b1f76,0xb3f233ff,0x33b3b34c,0xac572e8d,0x2e6bac32,0xb35433b8,0x3400b3ef,0x1d1b2810,
  0xb289324d,0x309eb0ee,0xb3ce33b5,0x2b0fac4b,0xb2f432c1,0x2fe8b04a,0xb3f033e1,0x27efa985,0xb34f3324,0x2e82af37,0xb3ff33fa,0x1eada4ce,
  0xb3983376,0x2d0badc8,0xb3fb33ff,0xa49c1de4,0x351c35f6,0xac93a617,0xb8a3b93c,0x308d2a16,0x32f43448,0xb160afa5,0xb6a4b7fe,0x353a3389,
  0x2fa53160,0xb448b2f4,0xb389b53a,0x37fe36a4,0x26172c93,0xb5f6b51c,0xaa16b08d,0x393c38a3,0x34c3358c,0xac47a5b2,0xb85fb8f3,0x304229b1,
  0x327e33fd,0xb106af26,0xb63cb785,0x34e7330f,0x2f263106,0xb3fdb27e,0xb30fb4e7,0x3785363c,0x25b22c47,0xb58cb4c3,0xa9b1b042,0x38f3385f,
  0x346a3523,0xabf6a54d,0xb81ab8a8,0x2fef294d,0x3209336b,0xb0acaea7,0xb5d4b70a,0x34933294,0x2ea730ac,0xb36bb209,0xb294b493,0x370a35d4,
  0x254d2bf6,0xb523b46a,0xa94dafef,0x38a8381a,0x341334bc,0xab5fa4e9,0xb7a6b85a,0x2f5928e8,0x319432da,0xb052ae28,0xb56ab68d,0x343e3219,
  0x2e283052,0xb2dab194,0xb219b43e,0x368d356a,0x24e92b5f,0xb4bcb413,0xa8e8af59,0x385a37a6,0x33783456,0xaac8a484,0xb715b80a,0x2ec32884,
  0x3120324a,0xaff2ada9,0xb4ffb60e,0x33d3319e,0x2da92ff2,0xb24ab120,0xb19eb3d3,0x360e34ff,0x24842ac8,0xb456b378,0xa884aec3,0x380a3715,
  0x32cd33e3,0xaa31a420,0xb682b76f,0x2e2d281f,0x30ac31bb,0xaf3fad2a,0xb493b58d,0x33283122,0x2d2a2f3f,0xb1bbb0ac,0xb122b328,0x358d3493,
  0x24202a31,0xb3e3b2cd,0xa81fae2d,0x376f3682,0x3223331c,0xa999a376,0xb5ebb6c6,0x2d972776,0x3039312d,0xae8dacac,0xb426b50b,0x327c30a6,
  0x2cac2e8d,0xb12db039,0xb0a6b27c,0x350b3426,0x23762999,0xb31cb223,0xa776ad97,0x36c635eb,0x317a3257,0xa902a2ad,0xb552b61a,0x2d0026ad,
  0x2f8c309f,0xaddcac2e,0xb371b487,0x31cf3029,0x2c2e2ddc,0xb09faf8c,0xb029b1cf,0x34873371,0x22ad2902,0xb257b17a,0xa6adad00,0x361a3552,
  0x30d23194,0xa86ba1e4,0xb4b7b56a,0x2c6a25e4,0x2ea73012,0xad2aab5f,0xb294b402,0x31222f59,0x2b5f2d2a,0xb012aea7,0xaf59b122,0x34023294,
  0x21e4286b,0xb194b0d2,0xa5e4ac6a,0x356a34b7,0x302c30d2,0xa7a9a11b,0xb41ab4b7,0x2ba7251b,0x2dc22f0c,0xac79aa63,0xb1b6b2f7,0x30742e5f,
  0x2a632c79,0xaf0cadc2,0xae5fb074,0x32f731b6,0x211b27a9,0xb0d2b02c,0xa51baba7,0x34b7341a,0x2f0c3012,0xa67ba052,0xb2f7b402,0x2a7a2452,
  0x2cde2df5,0xab91a967,0xb0d7b1e8,0x2f8b2d65,0x29672b91,0xadf5acde,0xad65af8b,0x31e830d7,0x2052267b,0xb012af0c,0xa452aa7a,0x340232f7,
  0x2dc22ea7,0xa54d9f12,0xb1b6b294,0x294d2311,0x2bf62cde,0xaa31a86b,0xafefb0d7,0x2e2d2c6a,0x286b2a31,0xacdeabf6,0xac6aae2d,0x30d72fef,
  0x1f12254d,0xaea7adc2,0xa311a94d,0x329431b6,0x2c792d2a,0xa4209d7f,0xb074b122,0x281f217f,0x2a312b91,0xa8d0a6e0,0xae2daf8b,0x2cce2ade,
  0x26e028d0,0xab91aa31,0xaadeacce,0x2f8b2e2d,0x1d7f2420,0xad2aac79,0xa17fa81f,0x31223074,0x2a632b5f,0xa1e49bdb,0xae5faf59,0x25e41fdb,
  0x286b2967,0xa6e0a4e9,0xac6aad65,0x2ade28e8,0x24e926e0,0xa967a86b,0xa8e8aade,0x2d652c6a,0x1bdb21e4,0xab5faa63,0x9fdba5e4,0x2f592e5f,
  0x27a9286b,0x9f1298b6,0xaba7ac6a,0x23111cb6,0x254d267b,0xa420a1e4,0xa94daa7a,0x281f25e4,0x21e42420,0xa67ba54d,0xa5e4a81f,0x2a7a294d,
  0x18b61f12,0xa86ba7a9,0x9cb6a311,0x2c6a2ba7,0x211b21e4,0x98b69248,0xa51ba5e4,0x1cb61648,0x1f122052,0x9d7f9bdb,0xa311a452,0x217f1fdb,
  0x1bdb1d7f,0xa0529f12,0x9fdba17f,0x24522311,0x124818b6,0xa1e4a11b,0x96489cb6,0x25e4251b,0xa11ba1e4,0x18b61248,0x251b25e4,0x9cb69648,
  0x9f12a052,0x1d7f1bdb,0x23112452,0xa17f9fdb,0x9bdb9d7f,0x20521f12,0x1fdb217f,0xa452a311,0x924898b6,0x21e4211b,0x16481cb6,0xa5e4a51b,
  0xa7a9a86b,0x1f1218b6,0x2ba72c6a,0xa3119cb6,0xa54da67b,0x242021e4,0x294d2a7a,0xa81fa5e4,0xa1e4a420,0x267b254d,0x25e4281f,0xaa7aa94d,
  0x98b69f12,0x286b27a9,0x1cb62311,0xac6aaba7,0xaa63ab5f,0x21e41bdb,0x2e5f2f59,0xa5e49fdb,0xa86ba967,0x26e024e9,0x2c6a2d65,0xaadea8e8,
  0xa4e9a6e0,0x2967286b,0x28e82ade,0xad65ac6a,0x9bdba1e4,0x2b5f2a63,0x1fdb25e4,0xaf59ae5f,0xac79ad2a,0x24201d7f,0x30743122,0xa81fa17f,
  0xaa31ab91,0x28d026e0,0x2e2d2f8b,0xacceaade,0xa6e0a8d0,0x2b912a31,0x2ade2cce,0xaf8bae2d,0x9d7fa420,0x2d2a2c79,0x217f281f,0xb122b074,
  0xadc2aea7,0x254d1f12,0x31b63294,0xa94da311,0xabf6acde,0x2a31286b,0x2fef30d7,0xae2dac6a,0xa86baa31,0x2cde2bf6,0x2c6a2e2d,0xb0d7afef,
  0x9f12a54d,0x2ea72dc2,0x2311294d,0xb294b1b6,0xaf0cb012,0x267b2052,0x32f73402,0xaa7aa452,0xacdeadf5,0x2b912967,0x30d731e8,0xaf8bad65,
  0xa967ab91,0x2df52cde,0x2d652f8b,0xb1e8b0d7,0xa052a67b,0x30122f0c,0x24522a7a,0xb402b2f7,0xb02cb0d2,0x27a9211b,0x341a34b7,0xaba7a51b,
  0xadc2af0c,0x2c792a63,0x31b632f7,0xb074ae5f,0xaa63ac79,0x2f0c2dc2,0x2e5f3074,0xb2f7b1b6,0xa11ba7a9,0x30d2302c,0x251b2ba7,0xb4b7b41a,
  0xb0d2b194,0x286b21e4,0x34b7356a,0xac6aa5e4,0xaea7b012,0x2d2a2b5f,0x32943402,0xb122af59,0xab5fad2a,0x30122ea7,0x2f593122,0xb402b294,
  0xa1e4a86b,0x319430d2,0x25e42c6a,0xb56ab4b7,0xb17ab257,0x290222ad,0x3552361a,0xad00a6ad,0xaf8cb09f,0x2ddc2c2e,0x33713487,0xb1cfb029,
  0xac2eaddc,0x309f2f8c,0x302931cf,0xb487b371,0xa2ada902,0x3257317a,0x26ad2d00,0xb61ab552,0xb223b31c,0x29992376,0x35eb36c6,0xad97a776,
  0xb039b12d,0x2e8d2cac,0x3426350b,0xb27cb0a6,0xacacae8d,0x312d3039,0x30a6327c,0xb50bb426,0xa376a999,0x331c3223,0x27762d97,0xb6c6b5eb,
  0xb2cdb3e3,0x2a312420,0x3682376f,0xae2da81f,0xb0acb1bb,0x2f3f2d2a,0x3493358d,0xb328b122,0xad2aaf3f,0x31bb30ac,0x31223328,0xb58db493,
  0xa420aa31,0x33e332cd,0x281f2e2d,0xb76fb682,0xb378b456,0x2ac82484,0x3715380a,0xaec3a884,0xb120b24a,0x2ff22da9,0x34ff360e,0xb3d3b19e,
  0xada9aff2,0x324a3120,0x319e33d3,0xb60eb4ff,0xa484aac8,0x34563378,0x28842ec3,0xb80ab715,0xb413b4bc,0x2b5f24e9,0x37a6385a,0xaf59a8e8,
  0xb194b2da,0x30522e28,0x356a368d,0xb43eb219,0xae28b052,0x32da3194,0x3219343e,0xb68db56a,0xa4e9ab5f,0x34bc3413,0x28e82f59,0xb85ab7a6,
  0xb46ab523,0x2bf6254d,0x381a38a8,0xafefa94d,0xb209b36b,0x30ac2ea7,0x35d4370a,0xb493b294,0xaea7b0ac,0x336b3209,0x32943493,0xb70ab5d4,
  0xa54dabf6,0x3523346a,0x294d2fef,0xb8a8b81a,0xb4c3b58c,0x2c4725b2,0x385f38f3,0xb042a9b1,0xb27eb3fd,0x31062f26,0x363c3785,0xb4e7b30f,
  0xaf26b106,0x33fd327e,0x330f34e7,0xb785b63c,0xa5b2ac47,0x358c34c3,0x29b13042,0xb8f3b85f,0xb51cb5f6,0x2c932617,0x38a3393c,0xb08daa16,
  0xb2f4b448,0x31602fa5,0x36a437fe,0xb53ab389,0xafa5b160,0x344832f4,0x3389353a,0xb7feb6a4,0xa617ac93,0x35f6351c,0x2a16308d,0xb93cb8a3,
};
__device__ __align__(128) const uint32_t c_img[2560] = {
  0x326d31ed,0x333b32dd,0x33c33388,0x33fe33ea,0x33c331ed,0x31ed33c3,0xa8b22d64,0xb33bb0c4,0x33ea31ed,0xad64301d,0xb2ddb388,0x315fa8b2,
  0x32dd31ed,0xb3feabc6,0x326dad64,0xad64326d,0x30c431ed,0xaed7b2dd,0x2bc63388,0xa248b3ea,0x2bc631ed,0x315fb3c3,0xb3ea2d64,0x2ed730c4,
  0xa8b231ed,0x3388b01d,0x301db388,0xb1ed28b2,0xb01d31ed,0x22482bc6,0x30c4ad64,0x3388b26d,0x33ea33fe,0x338833c3,0x32dd333b,0x31ed326d,
  0xb2ddb3fe,0xa248b01d,0x326d2ed7,0x338833ea,0x30c433fe,0xb33babc6,0xabc6b33b,0x33fe30c4,0xabc6b3fe,0x31ed32dd,0xb3eaaed7,0x333ba8b2,
  0xa8b233fe,0x2d64b3c3,0xb01d333b,0x315fb26d,0x301db3fe,0xb3fe301d,0x30c42ed7,0x2d64b3ea,0xb26d33fe,0x2ed72bc6,0x33c3b33b,0xa248b0c4,
  0x33c3b3fe,0x315fb2dd,0x28b2aed7,0xaed728b2,0xb0c4b15f,0xaed7b01d,0xabc6ad64,0xa248a8b2,0xabc6b15f,0x315f2bc6,0x33ea3388,0x2ed7326d,
  0x28b2b15f,0x338832dd,0xb01d2d64,0xb1edb3ea,0x301db15f,0x224833c3,0xb0c4b388,0x338830c4,0x326db15f,0xb33b301d,0x33c3ad64,0xb3fe28b2,
  0x33c3b15f,0xb1edabc6,0xa8b23388,0x333bb26d,0x33eab15f,0x2d64b2dd,0xb2dd2d64,0xb15f33ea,0x32ddb15f,0x33feb3c3,0x326db388,0x2d64b0c4,
  0x28b22248,0x2d642bc6,0x301d2ed7,0x315f30c4,0xb01da248,0xb3feb2dd,0xb0c4b33b,0x2d64a8b2,0x326d2248,0x2ed733c3,0xb3c3aed7,0xa248b26d,
  0xb3c3a248,0x315fb01d,0xa8b2333b,0xaed7b3ea,0x33ea2248,0xb388abc6,0x32dd2ed7,0xb1edb0c4,0xb2dda248,0x224832dd,0x326db33b,0xb38828b2,
  0x30c42248,0x333bb3c3,0xabc6aed7,0xb3fe326d,0xabc6a248,0xb1ed301d,0xb3ea333b,0xb33b33ea,0xb26d31ed,0xb33b32dd,0xb3c33388,0xb3fe33ea,
  0xb3c331ed,0xb1ed33c3,0x28b22d64,0x333bb0c4,0xb3ea31ed,0x2d64301d,0x32ddb388,0xb15fa8b2,0xb2dd31ed,0x33feabc6,0xb26dad64,0x2d64326d,
  0xb0c431ed,0x2ed7b2dd,0xabc63388,0x2248b3ea,0xabc631ed,0xb15fb3c3,0x33ea2d64,0xaed730c4,0x28b231ed,0xb388b01d,0xb01db388,0x31ed28b2,
  0x301d31ed,0xa2482bc6,0xb0c4ad64,0xb388b26d,0xb3ea33fe,0xb38833c3,0xb2dd333b,0xb1ed326d,0x32ddb3fe,0x2248b01d,0xb26d2ed7,0xb38833ea,
  0xb0c433fe,0x333babc6,0x2bc6b33b,0xb3fe30c4,0x2bc6b3fe,0xb1ed32dd,0x33eaaed7,0xb33ba8b2,0x28b233fe,0xad64b3c3,0x301d333b,0xb15fb26d,
  0xb01db3fe,0x33fe301d,0xb0c42ed7,0xad64b3ea,0x326d33fe,0xaed72bc6,0xb3c3b33b,0x2248b0c4,0xb3c3b3fe,0xb15fb2dd,0xa8b2aed7,0x2ed728b2,
  0x30c4b15f,0x2ed7b01d,0x2bc6ad64,0x2248a8b2,0x2bc6b15f,0xb15f2bc6,0xb3ea3388,0xaed7326d,0xa8b2b15f,0xb38832dd,0x301d2d64,0x31edb3ea,
  0xb01db15f,0xa24833c3,0x30c4b388,0xb38830c4,0xb26db15f,0x333b301d,0xb3c3ad64,0x33fe28b2,0xb3c3b15f,0x31edabc6,0x28b23388,0xb33bb26d,
  0xb3eab15f,0xad64b2dd,0x32dd2d64,0x315f33ea,0xb2ddb15f,0xb3feb3c3,0xb26db388,0xad64b0c4,0xa8b22248,0xad642bc6,0xb01d2ed7,0xb15f30c4,
  0x301da248,0x33feb2dd,0x30c4b33b,0xad64a8b2,0xb26d2248,0xaed733c3,0x33c3aed7,0x2248b26d,0x33c3a248,0xb15fb01d,0x28b2333b,0x2ed7b3ea,
  0xb3ea2248,0x3388abc6,0xb2dd2ed7,0x31edb0c4,0x32dda248,0xa24832dd,0xb26db33b,0x338828b2,0xb0c42248,0xb33bb3c3,0x2bc6aed7,0x33fe326d,
  0x2bc6a248,0x31ed301d,0x33ea333b,0x333b33ea,0x30c4315f,0x2ed7301d,0x2bc62d64,0x224828b2,0x2bc6315f,0xb15fabc6,0xb3eab388,0xaed7b26d,
  0xa8b2315f,0xb388b2dd,0x301dad64,0x31ed33ea,0xb01d315f,0xa248b3c3,0x30c43388,0xb388b0c4,0xb26d315f,0x333bb01d,0xb3c32d64,0x33fea8b2,
  0xb3c3315f,0x31ed2bc6,0x28b2b388,0xb33b326d,0xb3ea315f,0xad6432dd,0x32ddad64,0x315fb3ea,0xb2dd315f,0xb3fe33c3,0xb26d3388,0xad6430c4,
  0xa8b2a248,0xad64abc6,0xb01daed7,0xb15fb0c4,0x301d2248,0x33fe32dd,0x30c4333b,0xad6428b2,0xb26da248,0xaed7b3c3,0x33c32ed7,0x2248326d,
  0x33c32248,0xb15f301d,0x28b2b33b,0x2ed733ea,0xb3eaa248,0x33882bc6,0xb2ddaed7,0x31ed30c4,0x32dd2248,0xa248b2dd,0xb26d333b,0x3388a8b2,
  0xb0c4a248,0xb33b33c3,0x2bc62ed7,0x33feb26d,0x2bc62248,0x31edb01d,0x33eab33b,0x333bb3ea,0x326d31ed,0x333b32dd,0x33c33388,0x33fe33ea,
  0x33c331ed,0x31ed33c3,0xa8b22d64,0xb33bb0c4,0x33ea31ed,0xad64301d,0xb2ddb388,0x315fa8b2,0x32dd31ed,0xb3feabc6,0x326dad64,0xad64326d,
  0x30c431ed,0xaed7b2dd,0x2bc63388,0xa248b3ea,0x2bc631ed,0x315fb3c3,0xb3ea2d64,0x2ed730c4,0xa8b231ed,0x3388b01d,0x301db388,0xb1ed28b2,
  0xb01d31ed,0x22482bc6,0x30c4ad64,0x3388b26d,0x33ea33fe,0x338833c3,0x32dd333b,0x31ed326d,0xb2ddb3fe,0xa248b01d,0x326d2ed7,0x338833ea,
  0x30c433fe,0xb33babc6,0xabc6b33b,0x33fe30c4,0xabc6b3fe,0x31ed32dd,0xb3eaaed7,0x333ba8b2,0xa8b233fe,0x2d64b3c3,0xb01d333b,0x315fb26d,
  0x301db3fe,0xb3fe301d,0x30c42ed7,0x2d64b3ea,0xb26d33fe,0x2ed72bc6,0x33c3b33b,0xa248b0c4,0x33c3b3fe,0x315fb2dd,0x28b2aed7,0xaed728b2,
  0xb0c4315f,0xaed7301d,0xabc62d64,0xa24828b2,0xabc6315f,0x315fabc6,0x33eab388,0x2ed7b26d,0x28b2315f,0x3388b2dd,0xb01dad64,0xb1ed33ea,
  0x301d315f,0x2248b3c3,0xb0c43388,0x3388b0c4,0x326d315f,0xb33bb01d,0x33c32d64,0xb3fea8b2,0x33c3315f,0xb1ed2bc6,0xa8b2b388,0x333b326d,
  0x33ea315f,0x2d6432dd,0xb2ddad64,0xb15fb3ea,0x32dd315f,0x33fe33c3,0x326d3388,0x2d6430c4,0x28b2a248,0x2d64abc6,0x301daed7,0x315fb0c4,
  0xb01d2248,0xb3fe32dd,0xb0c4333b,0x2d6428b2,0x326da248,0x2ed7b3c3,0xb3c32ed7,0xa248326d,0xb3c32248,0x315f301d,0xa8b2b33b,0xaed733ea,
  0x33eaa248,0xb3882bc6,0x32ddaed7,0xb1ed30c4,0xb2dd2248,0x2248b2dd,0x326d333b,0xb388a8b2,0x30c4a248,0x333b33c3,0xabc62ed7,0xb3feb26d,
  0xabc62248,0xb1edb01d,0xb3eab33b,0xb33bb3ea,0xb26d31ed,0xb33b32dd,0xb3c33388,0xb3fe33ea,0xb3c331ed,0xb1ed33c3,0x28b22d64,0x333bb0c4,
  0xb3ea31ed,0x2d64301d,0x32ddb388,0xb15fa8b2,0xb2dd31ed,0x33feabc6,0xb26dad64,0x2d64326d,0xb0c431ed,0x2ed7b2dd,0xabc63388,0x2248b3ea,
  0xabc631ed,0xb15fb3c3,0x33ea2d64,0xaed730c4,0x28b231ed,0xb388b01d,0xb01db388,0x31ed28b2,0x301d31ed,0xa2482bc6,0xb0c4ad64,0xb388b26d,
  0xb3ea33fe,0xb38833c3,0xb2dd333b,0xb1ed326d,0x32ddb3fe,0x2248b01d,0xb26d2ed7,0xb38833ea,0xb0c433fe,0x333babc6,0x2bc6b33b,0xb3fe30c4,
  0x2bc6b3fe,0xb1ed32dd,0x33eaaed7,0xb33ba8b2,0x28b233fe,0xad64b3c3,0x301d333b,0xb15fb26d,0xb01db3fe,0x33fe301d,0xb0c42ed7,0xad64b3ea,
  0x326d33fe,0xaed72bc6,0xb3c3b33b,0x2248b0c4,0xb3c3b3fe,0xb15fb2dd,0xa8b2aed7,0x2ed728b2,0x29ed29ed,0x29ed29ed,0x29ed29ed,0x29ed29ed,
  0x2bc32a6d,0x2add2bea,0x23c628c4,0xa81da0b2,0x2bc32add,0xa3c6281d,0xabc3aadd,0x23c6a81d,0x29ed2b3b,0xabfea564,0x295fa6d7,0x1a482b88,
  0x25642b88,0xa564ab88,0x25642b88,0xa564ab88,0xa0b22bc3,0x2a6daadd,0xabea23c6,0x28c4281d,0xa8c42bea,0x2a6da0b2,0x28c4abea,0xaa6d20b2,
  0xab3b2bfe,0xa564295f,0x26d79a48,0x2b88a9ed,0x29ed29ed,0x29ed29ed,0x29ed29ed,0x29ed29ed,0xabc3aa6d,0xaaddabea,0xa3c6a8c4,0x281d20b2,
  0x2bc32add,0xa3c6281d,0xabc3aadd,0x23c6a81d,0xa9edab3b,0x2bfe2564,0xa95f26d7,0x9a48ab88,0x25642b88,0xa564ab88,0x25642b88,0xa564ab88,
  0x20b2abc3,0xaa6d2add,0x2beaa3c6,0xa8c4a81d,0xa8c42bea,0x2a6da0b2,0x28c4abea,0xaa6d20b2,0x2b3babfe,0x2564a95f,0xa6d71a48,0xab8829ed,
  0x295f295f,0x295f295f,0x295f295f,0x295f295f,0x23c628c4,0xa81da0b2,0xabc3aa6d,0xaaddabea,0xa3c6281d,0xabc3aadd,0x23c6a81d,0x2bc32add,
  0xa95f26d7,0x9a48ab88,0x29ed2b3b,0xabfea564,0xab882564,0x2b88a564,0xab882564,0x2b88a564,0xabea23c6,0x28c4281d,0x20b2abc3,0xaa6d2add,
  0xaa6d20b2,0xa8c42bea,0x2a6da0b2,0x28c4abea,0xa6d71a48,0xab8829ed,0xab3b2bfe,0xa564295f,0x295f295f,0x295f295f,0x295f295f,0x295f295f,
  0xa3c6a8c4,0x281d20b2,0x2bc32a6d,0x2add2bea,0xa3c6281d,0xabc3aadd,0x23c6a81d,0x2bc32add,0x295fa6d7,0x1a482b88,0xa9edab3b,0x2bfe2564,
  0xab882564,0x2b88a564,0xab882564,0x2b88a564,0x2beaa3c6,0xa8c4a81d,0xa0b22bc3,0x2a6daadd,0xaa6d20b2,0xa8c42bea,0x2a6da0b2,0x28c4abea,
  0x26d79a48,0x2b88a9ed,0x2b3babfe,0x2564a95f,0xabfe2bfe,0xabfe2bfe,0xabfe2bfe,0xabfe2bfe,0xaadd2bea,0xa3c628c4,0x281da0b2,0x2bc3aa6d,
  0xa81d2bc3,0x2adda3c6,0x281dabc3,0xaadd23c6,0x9a482b88,0x29edab3b,0xabfe2564,0x295f26d7,0x26d72b3b,0xa6d7ab3b,0x26d72b3b,0xa6d7ab3b,
  0x2a6d2add,0xabeaa3c6,0x28c4a81d,0x20b22bc3,0x2bea2a6d,0xa0b228c4,0xabeaaa6d,0x20b2a8c4,0x2b8829ed,0x2b3b2bfe,0x2564295f,0xa6d79a48,
  0xabfe2bfe,0xabfe2bfe,0xabfe2bfe,0xabfe2bfe,0x2addabea,0x23c6a8c4,0xa81d20b2,0xabc32a6d,0xa81d2bc3,0x2adda3c6,0x281dabc3,0xaadd23c6,
  0x1a48ab88,0xa9ed2b3b,0x2bfea564,0xa95fa6d7,0x26d72b3b,0xa6d7ab3b,0x26d72b3b,0xa6d7ab3b,0xaa6daadd,0x2bea23c6,0xa8c4281d,0xa0b2abc3,
  0x2bea2a6d,0xa0b228c4,0xabeaaa6d,0x20b2a8c4,0xab88a9ed,0xab3babfe,0xa564a95f,0x26d71a48,0x1a489a48,0x1a489a48,0x1a489a48,0x1a489a48,
  0x281da0b2,0x2bc3aa6d,0x2addabea,0x23c6a8c4,0x2adda3c6,0x281dabc3,0xaadd23c6,0xa81d2bc3,0x2bfea564,0xa95fa6d7,0x9a482b88,0x29edab3b,
  0x2b3ba6d7,0xab3b26d7,0x2b3ba6d7,0xab3b26d7,0x28c4a81d,0x20b22bc3,0xaa6daadd,0x2bea23c6,0x20b2a8c4,0x2bea2a6d,0xa0b228c4,0xabeaaa6d,
  0xa564a95f,0x26d71a48,0x2b8829ed,0x2b3b2bfe,0x1a489a48,0x1a489a48,0x1a489a48,0x1a489a48,0xa81d20b2,0xabc32a6d,0xaadd2bea,0xa3c628c4,
  0x2adda3c6,0x281dabc3,0xaadd23c6,0xa81d2bc3,0xabfe2564,0x295f26d7,0x1a48ab88,0xa9ed2b3b,0x2b3ba6d7,0xab3b26d7,0x2b3ba6d7,0xab3b26d7,
  0xa8c4281d,0xa0b2abc3,0x2a6d2add,0xabeaa3c6,0x20b2a8c4,0x2bea2a6d,0xa0b228c4,0xabeaaa6d,0x2564295f,0xa6d79a48,0xab88a9ed,0xab3babfe,
  0xa95fa95f,0xa95fa95f,0xa95fa95f,0xa95fa95f,0xa3c6a8c4,0x281d20b2,0x2bc32a6d,0x2add2bea,0x23c6a81d,0x2bc32add,0xa3c6281d,0xabc3aadd,
  0x295fa6d7,0x1a482b88,0xa9edab3b,0x2bfe2564,0x2b88a564,0xab882564,0x2b88a564,0xab882564,0x2beaa3c6,0xa8c4a81d,0xa0b22bc3,0x2a6daadd,
  0x2a6da0b2,0x28c4abea,0xaa6d20b2,0xa8c42bea,0x26d79a48,0x2b88a9ed,0x2b3babfe,0x2564a95f,0xa95fa95f,0xa95fa95f,0xa95fa95f,0xa95fa95f,
  0x23c628c4,0xa81da0b2,0xabc3aa6d,0xaaddabea,0x23c6a81d,0x2bc32add,0xa3c6281d,0xabc3aadd,0xa95f26d7,0x9a48ab88,0x29ed2b3b,0xabfea564,
  0x2b88a564,0xab882564,0x2b88a564,0xab882564,0xabea23c6,0x28c4281d,0x20b2abc3,0xaa6d2add,0x2a6da0b2,0x28c4abea,0xaa6d20b2,0xa8c42bea,
  0xa6d71a48,0xab8829ed,0xab3b2bfe,0xa564295f,0x29ed29ed,0x29ed29ed,0x29ed29ed,0x29ed29ed,0x2bc32a6d,0x2add2bea,0x23c628c4,0xa81da0b2,
  0x2bc32add,0xa3c6281d,0xabc3aadd,0x23c6a81d,0x29ed2b3b,0xabfea564,0x295fa6d7,0x1a482b88,0x25642b88,0xa564ab88,0x25642b88,0xa564ab88,
  0xa0b22bc3,0x2a6daadd,0xabea23c6,0x28c4281d,0xa8c42bea,0x2a6da0b2,0x28c4abea,0xaa6d20b2,0xab3b2bfe,0xa564295f,0x26d79a48,0x2b88a9ed,
  0x29ed29ed,0x29ed29ed,0x29ed29ed,0x29ed29ed,0xabc3aa6d,0xaaddabea,0xa3c6a8c4,0x281d20b2,0x2bc32add,0xa3c6281d,0xabc3aadd,0x23c6a81d,
  0xa9edab3b,0x2bfe2564,0xa95f26d7,0x9a48ab88,0x25642b88,0xa564ab88,0x25642b88,0xa564ab88,0x20b2abc3,0xaa6d2add,0x2beaa3c6,0xa8c4a81d,
  0xa8c42bea,0x2a6da0b2,0x28c4abea,0xaa6d20b2,0x2b3babfe,0x2564a95f,0xa6d71a48,0xab8829ed,0x9a481a48,0x9a481a48,0x9a481a48,0x9a481a48,
  0xa81d20b2,0xabc32a6d,0xaadd2bea,0xa3c628c4,0xaadd23c6,0xa81d2bc3,0x2adda3c6,0x281dabc3,0xabfe2564,0x295f26d7,0x1a48ab88,0xa9ed2b3b,
  0xab3b26d7,0x2b3ba6d7,0xab3b26d7,0x2b3ba6d7,0xa8c4281d,0xa0b2abc3,0x2a6d2add,0xabeaa3c6,0xa0b228c4,0xabeaaa6d,0x20b2a8c4,0x2bea2a6d,
  0x2564295f,0xa6d79a48,0xab88a9ed,0xab3babfe,0x9a481a48,0x9a481a48,0x9a481a48,0x9a481a48,0x281da0b2,0x2bc3aa6d,0x2addabea,0x23c6a8c4,
  0xaadd23c6,0xa81d2bc3,0x2adda3c6,0x281dabc3,0x2bfea564,0xa95fa6d7,0x9a482b88,0x29edab3b,0xab3b26d7,0x2b3ba6d7,0xab3b26d7,0x2b3ba6d7,
  0x28c4a81d,0x20b22bc3,0xaa6daadd,0x2bea23c6,0xa0b228c4,0xabeaaa6d,0x20b2a8c4,0x2bea2a6d,0xa564a95f,0x26d71a48,0x2b8829ed,0x2b3b2bfe,
  0xabfe2bfe,0xabfe2bfe,0xabfe2bfe,0xabfe2bfe,0xaadd2bea,0xa3c628c4,0x281da0b2,0x2bc3aa6d,0xa81d2bc3,0x2adda3c6,0x281dabc3,0xaadd23c6,
  0x9a482b88,0x29edab3b,0xabfe2564,0x295f26d7,0x26d72b3b,0xa6d7ab3b,0x26d72b3b,0xa6d7ab3b,0x2a6d2add,0xabeaa3c6,0x28c4a81d,0x20b22bc3,
  0x2bea2a6d,0xa0b228c4,0xabeaaa6d,0x20b2a8c4,0x2b8829ed,0x2b3b2bfe,0x2564295f,0xa6d79a48,0xabfe2bfe,0xabfe2bfe,0xabfe2bfe,0xabfe2bfe,
  0x2addabea,0x23c6a8c4,0xa81d20b2,0xabc32a6d,0xa81d2bc3,0x2adda3c6,0x281dabc3,0xaadd23c6,0x1a48ab88,0xa9ed2b3b,0x2bfea564,0xa95fa6d7,
  0x26d72b3b,0xa6d7ab3b,0x26d72b3b,0xa6d7ab3b,0xaa6daadd,0x2bea23c6,0xa8c4281d,0xa0b2abc3,0x2bea2a6d,0xa0b228c4,0xabeaaa6d,0x20b2a8c4,
  0xab88a9ed,0xab3babfe,0xa564a95f,0x26d71a48,0x3bfb3bff,0x3be53bf2,0x3bbf3bd4,0x3b873ba5,0x3bd03bfb,0x3b013b7c,0x399d3a60,0x378538bc,
  0x35173b52,0xbbc9b7c8,0xb074ba9b,0x3bfe391b,0x319e3b27,0xbbf3b979,0x363cb80a,0x3a2d3bc5,0xba093986,0x3a7eb8f8,0xbae5385f,0x3b3db77a,
  0xbabd393c,0x3bb0b699,0xbc00305b,0x3ba730d7,0xbb2a35c8,0xb8353bb2,0x3a64b1e8,0x3962bbf7,0xba90350b,0xba413bff,0x3602340e,0x3bf6bad8,
  0xac6aa5e4,0xb122af59,0xb402b294,0xb56ab4b7,0xb2deac9c,0xb7bdb5a5,0xb9b3b8d6,0xbb10ba73,0xbb96b676,0xb359bafe,0x3bec3884,0x2a163a29,
  0xbbe0b72c,0x2f27b9d6,0x3b5e3ae8,0xb91633a2,0xb941b9c9,0x38ad3a45,0xb80fbab3,0x36d23b13,0xb850ba0d,0x346f3b4a,0x1fdbbbed,0xb4ab3be8,
  0x3721bb76,0xbace3463,0xb8d13bdd,0x39ebadfb,0x3894bb98,0xb8fd281f,0xbb6a3bbd,0x2e2d3825,0x3b3f3b65,0x3ae83b16,0x3a813ab6,0x3a0d3a49,
  0x3263356a,0xad972b43,0xb5dfb359,0xb8eeb7f3,0xa9b139aa,0xbbedba25,0x3340b889,0x3b983afb,0xbaa2aa16,0xb4cfbb8e,0x3c0038ad,0xb44b38e5,
  0xbb853625,0x3bbdb4c3,0xbbe432ad,0x3bfbaf8b,0xbaacb6d2,0x39243954,0xb65fbace,0x2fbd3bb8,0xb9661648,0xba603bf8,0x383a31cf,0x3b27bbb3,
  0x3219b9eb,0xbb1836f4,0xb9903be5,0x37dd3010,0xb6c6b61a,0xb80ab76f,0xb8a8b85a,0xb93cb8f3,0xbbd7bb87,0xbbf8bbfd,0xbb71bbc9,0xba4dbaf1,
  0xbbfeb9a6,0x305bb91f,0x3bcb3a97,0xb50b37d2,0xb87abbfe,0x3ba13546,0x24523a7e,0xbbb5ba54,0xb576bb63,0x340e3ba3,0xb13bbbd3,0x2c9c3bf2,
  0x386abb3d,0xba2139f8,0x3b57b835,0xbbf13432,0x39e7bc00,0xb8d6adc9,0xbacb3bde,0x372c3457,0x3bdab962,0x3764bb35,0xb9c03122,0xbaf73bef,
  0x398b39cd,0x38fd3946,0x386538b2,0x37853815,0xba85b9c9,0xbb92bb1e,0xbbfebbdd,0xbbc2bbf5,0xb66b3682,0xbb01bb94,0x387fb371,0x3a2d3beb,
  0xbac7bb76,0x3a00ad33,0x36bb3bd4,0xbbeab79b,0xbc0026ad,0x3bf32c38,0xbbd6b109,0x3ba733eb,0x3153bbff,0xb70a3b9e,0x396bba9b,0xbade390c,
  0xb5d4b5bc,0xbbb03b2c,0x32013830,0x3bf6ba67,0x3bccbb52,0x2c06b92e,0xbb83385f,0xb8c73bab,0xb9c5b982,0xba41ba04,0xbab0ba7a,0xbb10bae1,
  0xb8a3b986,0xb52fb74e,0xa94db1e8,0x33d32e91,0xbb54bb4f,0x37bdb523,0x3a9e3bc8,0xb916308d,0x3840b5c8,0x394a3bf9,0xbb42b294,0xb0a6bb0a,
  0x251bbbff,0xaf273bfc,0x327cbbe6,0xb4ab3bc0,0x3be325e4,0xbb2fb4e7,0x39e33884,0xb81aba35,0x3b73bb78,0xb46fb715,0xbbdc3ad1,0x2e2d38cc,
  0x33283676,0x3bfcba19,0x3581bab3,0xba6b3493,0x363136dd,0x34cf3581,0x32c6341a,0x2fbd3153,0xbae1bb65,0xb970ba39,0xb715b889,0xb16cb4f3,
  0xb9a12a7a,0xb924bbfe,0x3a933042,0x37dd3bcc,0x308db9aa,0x3b453b07,0xb94632ad,0xb845bbfa,0xbb68b55e,0x3b1836bb,0xbabab805,0x3a4d38a3,
  0x3bc0b625,0xbbfe2ec3,0x3b9431cf,0xba89b742,0x9cb6b95d,0xbbf8396b,0xb1b63a5c,0x3bb5b840,0x38cc9648,0x3b81bbac,0xac38b85a,0xbbce3933,
  0xbb60bb3a,0xbba1bb83,0xbbd2bbbc,0xbbf1bbe3,0x3815361a,0x39df3907,0x3b2c3a97,0x3be23b9c,0xb9afbbfd,0x3a21294d,0x388e3bee,0xbaf7b328,
  0x3beb39a6,0xb6af37a6,0xba04bbd3,0x3ac42d00,0x360ebb89,0xb7643b42,0x3855baeb,0xb8ee3a85,0x33eb3b63,0x28e8bbf5,0xb5233bde,0x389ebb21,
  0x3c00b9f0,0x2d97b9e3,0xbbdf38db,0xb44b3ac7,0xba673c00,0x358d3487,0x3bfcbab6,0x330fba15,0x3b7a3bf1,0x394a3a93,0x33893764,0xb3d39cb6,
  0x3afb3be2,0x35eb3946,0xb4c328e8,0xbaa9b8cc,0x27763af7,0xbb2fbaba,0x3a76ad97,0x30a63b60,0xaf8b3ac4,0xb994bb94,0x3bf8358d,0xb8743815,
  0xbb4c38ee,0x3bfcb1b6,0xbad5b4cf,0x381a39af,0xbbb3389e,0x3b592c38,0xb76fb970,0xb24b3beb,0xb9d2344b,0xbb923bd2,0xb0f03924,0x3a6bb60e,
  0xb8f3330f,0xbc003b2c,0xb91f3b45,0x323233eb,0xb5b1afbd,0xba00b88e,0xbbc6bb18,0xbbc2bc00,0xb7d2b16c,0xbb6fba04,0xbba3bbfe,0xb86fba67,
  0xbbffb7dd,0x370ab855,0x38b73bf8,0xbbeab631,0xbbf2b845,0x39bcb523,0x2dc93b81,0xbaa5bae1,0xb68dba4d,0xac063bdf,0x382abba1,0xbade39a1,
  0xb457ba89,0xb6543bfc,0x3b16b9df,0xbbd8308d,0x397dbbb5,0xb52fb2c6,0xbbe73a21,0xb8c73b68,0x3a49bbce,0x2311b715,0xba2536af,0xbbd93bc0,
  0xb958b785,0xbb81ba9e,0xbbefbbf3,0xba89bb73,0xbbf7bbc2,0xb9b8bb42,0xaf59b70a,0x384a3328,0xbb8bba2d,0x39dfb27c,0x34263bb0,0xbbceb98b,
  0xb4b7bbea,0x3b6c39e3,0xbafe2c06,0x3185ba85,0xaadebba7,0xb6af3bdc,0x3a58ba41,0xbbe2366b,0x3a29bade,0xbc003581,0x3a45352f,0xb2f7bac7,
  0x3b37bbf6,0x28e8b865,0xbaee37bd,0xbac43c00,0x3b13b8c7,0x3b5cbbfe,0x3463b94a,0xb8993153,0xb9f4bb10,0xb58db87f,0x3029af27,0x389e35d4,
  0x2dfbb3d3,0x399936bb,0x3bf23b2f,0x3ac13bcc,0x3552b916,0x39703bd6,0xbbbab46f,0x330fb9c5,0x3ba530a6,0xb5f7396b,0xb7c8bbfc,0x3be138a3,
  0x3bfdb4ab,0xbb45b201,0x38e038fd,0xb16cbb54,0x391b381a,0xa17fbb83,0xb8f83b92,0x3bcfb840,0x36e82e2d,0x3bfebab0,0x37febb01,0xb845251b,
  0xb77a3a6b,0x3648294d,0x3bb2ba00,0x3a8cbbe3,0xb742b93c,0x2311b340,0x37a6340e,0x3aa93966,0x3b963a4d,0x3b7f3c00,0x380f3a21,0xb0be3219,
  0x3933b50b,0x35eb3be4,0xbbf5b8d6,0x3874b6c6,0x39413bb5,0xbbffb65f,0x38d1b764,0x33ba3bd7,0x3b9c2c9c,0xb994b83a,0x34873ae8,0x324bbbfe,
  0xb7213bf1,0x3b47b990,0xbbbf2d97,0x38c1387a,0x2d00372c,0x3b59b8a8,0x3a39bbed,0xb232b576,0xbbfb3af7,0xb9743b71,0x307434cf,0x3adbb86a,
  0x3b213a0d,0x3c003bcb,0x3b073bbd,0x386f39e7,0x351738ee,0xb599a452,0xbae5b924,0xbbe9bbda,0x3a153b98,0xbb6fb13b,0x2ec3ba60,0x3aa53b3f,
  0xba09344b,0xa884bb57,0x3a643b18,0xbbc3b263,0xb4f33bfb,0x39bcbacb,0xbbac380a,0x3bd8a9b1,0xbb2aafbd,0x36a439c0,0x3402bbf8,0xba6f3aa2,
  0xbbfa3b27,0xb6543a81,0x3907b05b,0x3bd9bb85,0x2c6ab7dd,0xb9da35df,0xbbec3ba1,0xb8203aac,0x3bf53b87,0x3b6c3bec,0x392e3a7e,0x32f73721,
  0xb9e7b785,0xbbfcbb5e,0xba81bbb0,0xb43eb894,0x379b3bfe,0xbc00b80f,0x374eb835,0x38993bfb,0xbb3fba2d,0x3b329fdb,0xb3403a41,0xb8eabbd0,
  0xb90c3b3d,0x3b5cb8d1,0xbbf93122,0x3ac13517,0x29b1bba7,0xb94f3b6a,0x3be4b7bd,0xbaf4b19e,0xbbab3962,0xb9993bbf,0x34e73359,0x3be1ba09,
  0x3b85bbf6,0x353ab99d,0xb83a2f27,0xbbf03abd,0x2e91356a,0xb5f7b074,0xba19b8ad,0xbbcfbb2a,0xb966bb10,0xaba7b63c,0x38a8346f,0x3bb73a90,
  0xbb0aaa16,0xa17fbae5,0x3b1e3ace,0xba8c2c6a,0x36c6b916,0x36ff3c00,0xbbcbb8fd,0x3a50b2de,0xba35b6d2,0x36483a64,0x2d33bbe5,0xb84a3b96,
  0x3bfeb4ab,0xb9fcb602,0x313b3b01,0x37e8bbe0,0x3493b9eb,0xb9b83402,0xbb9e3bc9,0xb1853941,0x35762e2d,0x3b90b9b3,0x3acbbbf3,0x2fefb850,
  0x3a543bcf,0x2884374e,0xb9f8b648,0xbbe9bbab,0x398b3bb7,0xb4db3340,0xbbdcb9fc,0xb911bb85,0xb4323a8c,0xb6a4bbf9,0x3b3539b8,0xbbc3ae91,
  0xb66b3a50,0xad65bbe4,0x38653b90,0xbb0db966,0xbbef384a,0x39da34e7,0x2b43bb6c,0xba6f3b0a,0xbc0037e8,0x3759383a,0x387fbbfc,0xbbf636c6,
  0xb7f33185,0xbb7f3a19,0xbb8e3c00,0xb8203a35,0xb5d42fef,0xba1d38a8,0xbbd63b32,0xbba93bfe,0xb8e5b2f7,0xbbffbb1e,0xb954bb5c,0x30beb493,
  0xb9c5b43e,0xbb9fbbcb,0xb201b94f,0x3a313576,0xbbb8b899,0x3b47ad33,0xb6f43999,0xb3babbf5,0xbb54b8ea,0x3bf9313b,0xbab0353a,0x3790b9e7,
  0xb010bac1,0xb9743b9e,0x3bfdb5f7,0xb8c1b79b,0x251bbaf4,0xbb1b3acb,0x3a9e2ba7,0x2e5fbb3f,0x3af1bbe1,0x3599b92e,0xb546a17f,0xbadb390c,
  0x3b73bbf0,0x3929ba81,0x327cb6ff,0xb49f29b1,0xb825baa9,0x353aaec3,0x3b7c3994,0x3af43bfa,0x360eb0be,0x3bf43a64,0x388e3b47,0xb7372c6a,
  0x38bcb874,0x2ba73bac,0xb979bb59,0x3bf03742,0x3c0033ba,0xbb043402,0x3855b974,0xacce3b96,0x3bc5b24b,0xb6ffb907,0xb6993c00,0x3bb7b933,
  0x363138c1,0x3902bbec,0xbbdf3599,0x34ff3941,0x30d73232,0x39fcb7a6,0x3bffbb6f,0x3a50bb9c,0xb9a13adb,0xb47b380f,0x32c62884,0x3937b721,
  0x3ad8386f,0x3b903bf5,0x35a539bc,0xb7e8ad00,0x3b683be9,0x2ef538d1,0xba93b6a4,0xbb24bbfb,0x3a733aa5,0xbbfcb487,0x39d6b654,0xafef3b21,
  0x1cb63bc3,0xb7b2bbbf,0x3aba39da,0xbbfab517,0xb3a23bd8,0x3b32ba39,0xbb4a2311,0x343e3a15,0xbb603a6f,0x3a3d3074,0x31b6bb7f,0xbb9a3a09,
  0xbbe83bd9,0xb94f3b07,0xa81f35eb,0x38eab4f3,0xb9af3820,0xbbae3ae5,0xbbd23bff,0xba113b2a,0x319e389e,0xb929b426,0xbc00bb45,0xb911bb37,
  0xbbffbac1,0xb805bafe,0x382a217f,0x3bfd3b13,0xbabd330f,0x34dbba58,0x36023bfe,0xbb0db9f4,0xb68dbbe1,0x3a5c3a45,0xbbe7b648,0x3b89adfb,
  0xba90b16c,0x2d653aee,0x39b3bb81,0xbbf63552,0x397dbbcf,0xbbbc3463,0x338939b8,0x39f0bba5,0x32deb845,0xb7593029,0xbb5e39df,0xbba93bfd,
  0x3b7aba8c,0x3beebbf2,0x3a76bb6c,0x36ddb91b,0xbbe0ba89,0xba1dbbba,0x1fdbb6af,0x3a3136e8,0xa776b84a,0x3aeb37c8,0x3ad53c00,0xaa7a377a,
  0xb850bbce,0x3b9f38e0,0xbb6a28e8,0x3790b958,0x3b4cb185,0xb8db38f8,0x30f0bb5c,0x355e3bf7,0x3894bbe2,0xbbf937fe,0x399d358d,0x2e5fbb8b,
  0x39d232f7,0x341abbb2,0xbbc63999,0x395d34b7,0x3bd0bac4,0x3b1bbbef,0x363cb970,0xb49faade,0xb5b13899,0x30422f59,0x38b7b5f7,0x3b3aba29,
  0x3219b3d3,0x3b0438b7,0x3b713bfc,0x34ff397d,0x36e83aa9,0xb8b2adc9,0xbbefbb59,0xb5bcba49,0x3bd730a6,0xb902382a,0xa452bb92,0x39373b7a,
  0xb9583874,0x3371bb16,0x34263c00,0xb982bafb,0x387a381a,0x347bbbe7,0xbb573a00,0x3b242776,0xbb8b324b,0x31093a25,0x3a58bb6f,0xbb4f2f8b,
  0xb86a3a6b,0x2ef53389,0x39c0b70a,0x3bfabb4c,0xaadeb232,0xb83034c3,0xbaee39bc,0xbbff3bb3,0x3bda3bc2,0x37b23a76,0xb5df2c06,0xbb9ab9d2,
  0xbb37b86f,0xba7abbf8,0x3029b654,0x3b7838f3,0x32633bea,0xba3dbad5,0x3c00352f,0xba1135b1,0xb9f4baa5,0x3bc8376f,0xbbba2311,0x39cdb7d2,
  0xbaa23ade,0x3baeb0f0,0xb65fb94a,0xb7373bff,0x3552bbd8,0xbbe6391f,0x38e035eb,0x3682bbf2,0xbaac38c7,0xbbf43bc6,0xb9903b2f,0xacce368d,
  0x3bfdbbd9,0x3ad1bba3,0x37feb994,0x26adb457,0x38a33b9a,0xb8dba452,0xbb83bbae,0x2a7ab86a,0x37423b78,0xbab6b426,0xb907bbe6,0x39aa2ade,
  0xb8403a11,0x341abb57,0x294d3bf4,0xb55ebbda,0xb93339cd,0x3889ba58,0xb7a63ad1,0x3625bb37,0xbbe33737,0x304239c0,0x3b42bb04,0xb95db263,
  0xbb9c3682,0xb2ad3aee,0x3bf5b8b2,0x1648b9f4,0xb3282cce,0xb80535df,0xb9e33902,0xbb3a3aa2,0xad0026ad,0xb1cf3029,0xb4873371,0xb61a3552,
  0xba85b4ff,0xba5cbc00,0x3581b47b,0x3bfd3aac,0xbb21b5bc,0xb85abbba,0x3a393109,0x39a63bfd,0xbac7b937,0x3bbc365f,0xbbfeaef5,0x3b89b219,
  0xba15b982,0x3a9738e0,0xbb07b830,0x3b6336e8,0x3153bb24,0xbbee3990,0x36bb37b2,0x39f0bbd7,0x34f3bb4f,0xbbd337fe,0xaec33a7a,0x3c00b958,
  0x3bccbbfa,0x3aebbb71,0x396bba3d,0x36ddb87a,0x3bfabbff,0x3bdebbef,0x3bacbbc8,0x3b65bb8b,0x3bc03911,0x38303b6a,0xb946ad65,0xbb4fbbd0,
  0x3a353bfd,0xb85f30f0,0xbb1ebbbc,0x35c8b5b1,0x38cc3b0d,0xba7ab99d,0x3b943759,0xbbffb19e,0xb4933b89,0x31e8bbc6,0xad333bee,0xa5e4bbff,
  0xb8153bf6,0x3bc8b63c,0xac38ba1d,0xbb783abd,0xbbf539f0,0x329438b7,0x3b9ebaeb,0xb676b68d,0xbbeb3ba9,0xbbe63c00,0xbb2c3b9f,0xb9cd3a90,
  0xb79b36dd,0xb884382a,0xb92e38db,0xb9c9397d,0x33eb3a31,0xbad1b602,0xba04bbf9,0x3682b2de,0xb90c2a7a,0xbab3bbe7,0x374eb41a,0x3b763b7a,
  0xba673790,0x38b2b9b3,0xb5233b1b,0x26adbbe0,0xbbabb55e,0x3bdd3389,0xbbf9b042,0x3bff2776,0xbae12e5f,0xb3713b5e,0x3bfcb929,0xb5bcb850,
  0xae91b95d,0xbbd43a76,0x34e73805,0x3b52bb4c,0x308db49f,0xb1091fdb,0xb71534db,0xb9823894,0x3b0abb3a,0x3a9bbad5,0x3a19ba5c,0x3986b9d2,
  0x2f8bb7e8,0x3bde3979,0x376f3b32,0xb9aab0d7,0x3bb83b24,0xb1223855,0xbbfdba3d,0xaa16b9a1,0x3bb3afef,0xbab63699,0x391fb94f,0xb6253ad8,
  0x30103bfa,0xb359bbdf,0x35463bae,0xb6d2bb68,0x38f3343e,0x3889bbff,0xbba3353a,0x96483a73,0xbaf13b9a,0x38ad32c6,0x39f8bbf4,0xb9eb9cb6,
  0xb7d238ea,0xb2ad35a5,0x2dc92ba7,0x361ab3a2,0xba543a11,0xbace3a93,0xbb353b04,0xbb873b60,0x3bf23af4,0x31cf39d6,0xbb16b6ff,0xb9a6bbe8,
  0xb4323737,0xbbe5baba,0x2b43b902,0x3bfe39af,0x34573bf0,0xb85abb4a,0x3a2539fc,0xbb63b825,0xbbef2cce,0x3bc9b1b6,0xbb8e347b,0x3b3db60e,
  0xba493bb7,0x3a97a81f,0x34c3bb90,0xbc0038bc,0xb7f3b4ff,0xba7e3bd2,0x39542ef5,0x3962bc00,0xbafb3a50,0xbbd33b7c,0xbbf83bfc,0xbb653bc5,
  0x38e5b937,0x3835b88e,0x36f4b7b2,0x356ab631,0xbb13bbe9,0x31e8b6f4,0x3bf239da,0x36763af1,0x3be83911,0x340e3ab0,0xbb7cb759,0xb72cbb73,
  0x2dfbbbc3,0x32943bfd,0xb7c8bb7f,0x39c93a54,0x38253b0d,0xb8d6ba9e,0x39793a1d,0xba0db98b,0x3ba5ba6f,0xb884b546,0xb8f83bff,0x3b76b432,
  0xb8bc3bf6,0x3ae8b27c,0x3699bb9f,0xbb98366b,0x391bb820,0x3ab3b9f8,0x3bb2bb47,0x3bffbbef,0xbbc53ba9,0xbbed3bdc,0xbbff3bf9,0xbbfb3c00,
  0x377ab0be,0x3bdd3b35,0x2f593974,0xbb52b7f3,0x30d73a31,0xbbbdb865,0xb5a5bb1b,0x3b2735d4,0x3bf733ba,0xbbd42b43,0x3afeb599,0xb98638e5,
  0xbad83790,0x3a60b87f,0xb9d63929,0x393cb9c5,0x34b738c1,0x3a9bbb8e,0xba45a884,0xb5c83bb8,0xba732e5f,0xb80a3bd6,0x3b4ab4db,0x350bbb54,
  0xba293adb,0xb85f3954,0xb46336a4,0x25e43010,0x33a2b49f,0x305bb201,0x281fad65,0xac9c251b,0x3f803f80,0x3f803f80,0x3f803f80,0x3f803f80,
  0x3f803f80,0x3f803f80,0x3f803f80,0x3f803f80,0x3f803f80,0x3f803f80,0x3f803f80,0x3f803f80,0x3f803f80,0x3f803f80,0x3f803f80,0x3f803f80,
  0x3f803f80,0x3f803f80,0x3f803f80,0x3f803f80,0x3f803f80,0x3f803f80,0x3f803f80,0x3f803f80,0x3f803f80,0x3f803f80,0x3f803f80,0x3f803f80,
  0x3f803f80,0x3f803f80,0x3f803f80,0x3f803f80,0x3f803f80,0x3f803f80,0x3f803f80,0x3f803f80,0x3f803f80,0x3f803f80,0x3f803f80,0x3f803f80,
  0x3f803f80,0x3f803f80,0x3f803f80,0x3f803f80,0x3f803f80,0x3f803f80,0x3f803f80,0x3f803f80,0x3f803f80,0x3f803f80,0x3f803f80,0x3f803f80,
  0x3f803f80,0x3f803f80,0x3f803f80,0x3f803f80,0x3f803f80,0x3f803f80,0x3f803f80,0x3f803f80,0x3f803f80,0x3f803f80,0x3f803f80,0x3f803f80,
  0x3f803f80,0x3f803f80,0x3f803f80,0x3f803f80,0x3f803f80,0x3f803f80,0x3f803f80,0x3f803f80,0x3f803f80,0x3f803f80,0x3f803f80,0x3f803f80,
  0x3f803f80,0x3f803f80,0x3f803f80,0x3f803f80,0x3f803f80,0x3f803f80,0x3f803f80,0x3f803f80,0x3f803f80,0x3f803f80,0x3f803f80,0x3f803f80,
  0x3f803f80,0x3f803f80,0x3f803f80,0x3f803f80,0x3f803f80,0x3f803f80,0x3f803f80,0x3f803f80,0x3f803f80,0x3f803f80,0x3f803f80,0x3f803f80,
  0x3f803f80,0x3f803f80,0x3f803f80,0x3f803f80,0x3f803f80,0x3f803f80,0x3f803f80,0x3f803f80,0x3f803f80,0x3f803f80,0x3f803f80,0x3f803f80,
  0x3f803f80,0x3f803f80,0x3f803f80,0x3f803f80,0x3f803f80,0x3f803f80,0x3f803f80,0x3f803f80,0x3f803f80,0x3f803f80,0x3f803f80,0x3f803f80,
  0x3f803f80,0x3f803f80,0x3f803f80,0x3f803f80,0x3f803f80,0x3f803f80,0x3f803f80,0x3f803f80,0x3f803f80,0x3f803f80,0x3f803f80,0x3f803f80,
  0x3f803f80,0x3f803f80,0x3f803f80,0x3f803f80,0x3f803f80,0x3f803f80,0x3f803f80,0x3f803f80,0x3f803f80,0x3f803f80,0x3f803f80,0x3f803f80,
  0x3f803f80,0x3f803f80,0x3f803f80,0x3f803f80,0x3f803f80,0x3f803f80,0x3f803f80,0x3f803f80,0x3f803f80,0x3f803f80,0x3f803f80,0x3f803f80,
  0x3f803f80,0x3f803f80,0x3f803f80,0x3f803f80,0x3f803f80,0x3f803f80,0x3f803f80,0x3f803f80,0x3f803f80,0x3f803f80,0x3f803f80,0x3f803f80,
  0x3f803f80,0x3f803f80,0x3f803f80,0x3f803f80,0x3f803f80,0x3f803f80,0x3f803f80,0x3f803f80,0x3f803f80,0x3f803f80,0x3f803f80,0x3f803f80,
  0x3f803f80,0x3f803f80,0x3f803f80,0x3f803f80,0x3f803f80,0x3f803f80,0x3f803f80,0x3f803f80,0x3f803f80,0x3f803f80,0x3f803f80,0x3f803f80,
  0x3f803f80,0x3f803f80,0x3f803f80,0x3f803f80,0x3f803f80,0x3f803f80,0x3f803f80,0x3f803f80,0x3f803f80,0x3f803f80,0x3f803f80,0x3f803f80,
  0x3f803f80,0x3f803f80,0x3f803f80,0x3f803f80,0x3f803f80,0x3f803f80,0x3f803f80,0x3f803f80,0x3f803f80,0x3f803f80,0x3f803f80,0x3f803f80,
  0x3f803f80,0x3f803f80,0x3f803f80,0x3f803f80,0x3f803f80,0x3f803f80,0x3f803f80,0x3f803f80,0x3f803f80,0x3f803f80,0x3f803f80,0x3f803f80,
  0x3f803f80,0x3f803f80,0x3f803f80,0x3f803f80,0x3f803f80,0x3f803f80,0x3f803f80,0x3f803f80,0x3f803f80,0x3f803f80,0x3f803f80,0x3f803f80,
  0x3f803f80,0x3f803f80,0x3f803f80,0x3f803f80,0x3f803f80,0x3f803f80,0x3f803f80,0x3f803f80,0x3f803f80,0x3f803f80,0x3f803f80,0x3f803f80,
  0x3f803f80,0x3f803f80,0x3f803f80,0x3f803f80,0x3f803f80,0x3f803f80,0x3f803f80,0x3f803f80,0x3f803f80,0x3f803f80,0x3f803f80,0x3f803f80,
  0x3f803f80,0x3f803f80,0x3f803f80,0x3f803f80,0x3f803f80,0x3f803f80,0x3f803f80,0x3f803f80,0x3f803f80,0x3f803f80,0x3f803f80,0x3f803f80,
  0x3f803f80,0x3f803f80,0x3f803f80,0x3f803f80,0x3f803f80,0x3f803f80,0x3f803f80,0x3f803f80,0x3f803f80,0x3f803f80,0x3f803f80,0x3f803f80,
  0x3f803f80,0x3f803f80,0x3f803f80,0x3f803f80,0x3f803f80,0x3f803f80,0x3f803f80,0x3f803f80,0x3f803f80,0x3f803f80,0x3f803f80,0x3f803f80,
  0x3f803f80,0x3f803f80,0x3f803f80,0x3f803f80,0x3f803f80,0x3f803f80,0x3f803f80,0x3f803f80,0x3f803f80,0x3f803f80,0x3f803f80,0x3f803f80,
  0x3f803f80,0x3f803f80,0x3f803f80,0x3f803f80,0x3f803f80,0x3f803f80,0x3f803f80,0x3f803f80,0x3f803f80,0x3f803f80,0x3f803f80,0x3f803f80,
  0x3f803f80,0x3f803f80,0x3f803f80,0x3f803f80,0x3f803f80,0x3f803f80,0x3f803f80,0x3f803f80,0x3f803f80,0x3f803f80,0x3f803f80,0x3f803f80,
  0x3f803f80,0x3f803f80,0x3f803f80,0x3f803f80,0x3f803f80,0x3f803f80,0x3f803f80,0x3f803f80,0x3f803f80,0x3f803f80,0x3f803f80,0x3f803f80,
  0x3f803f80,0x3f803f80,0x3f803f80,0x3f803f80,0x3f803f80,0x3f803f80,0x3f803f80,0x3f803f80,0x3f803f80,0x3f803f80,0x3f803f80,0x3f803f80,
  0x3f803f80,0x3f803f80,0x3f803f80,0x3f803f80,0x3f803f80,0x3f803f80,0x3f803f80,0x3f803f80,0x3f803f80,0x3f803f80,0x3f803f80,0x3f803f80,
  0x3f803f80,0x3f803f80,0x3f803f80,0x3f803f80,0x3f803f80,0x3f803f80,0x3f803f80,0x3f803f80,0x3f803f80,0x3f803f80,0x3f803f80,0x3f803f80,
  0x3f803f80,0x3f803f80,0x3f803f80,0x3f803f80,0x3f803f80,0x3f803f80,0x3f803f80,0x3f803f80,0x3f803f80,0x3f803f80,0x3f803f80,0x3f803f80,
  0x3f803f80,0x3f803f80,0x3f803f80,0x3f803f80,0x3f803f80,0x3f803f80,0x3f803f80,0x3f803f80,0x3f803f80,0x3f803f80,0x3f803f80,0x3f803f80,
  0x3f803f80,0x3f803f80,0x3f803f80,0x3f803f80,0x3f803f80,0x3f803f80,0x3f803f80,0x3f803f80,0x3f803f80,0x3f803f80,0x3f803f80,0x3f803f80,
  0x3f803f80,0x3f803f80,0x3f803f80,0x3f803f80,0x3f803f80,0x3f803f80,0x3f803f80,0x3f803f80,0x3f803f80,0x3f803f80,0x3f803f80,0x3f803f80,
  0x3f803f80,0x3f803f80,0x3f803f80,0x3f803f80,0x3f803f80,0x3f803f80,0x3f803f80,0x3f803f80,0x3f803f80,0x3f803f80,0x3f803f80,0x3f803f80,
  0x3f803f80,0x3f803f80,0x3f803f80,0x3f803f80,0x3f803f80,0x3f803f80,0x3f803f80,0x3f803f80,0x3f803f80,0x3f803f80,0x3f803f80,0x3f803f80,
  0x3f803f80,0x3f803f80,0x3f803f80,0x3f803f80,0x3f803f80,0x3f803f80,0x3f803f80,0x3f803f80,0x3f803f80,0x3f803f80,0x3f803f80,0x3f803f80,
  0x3f803f80,0x3f803f80,0x3f803f80,0x3f803f80,0x3f803f80,0x3f803f80,0x3f803f80,0x3f803f80,0x3f803f80,0x3f803f80,0x3f803f80,0x3f803f80,
  0x3f803f80,0x3f803f80,0x3f803f80,0x3f803f80,0x3f803f80,0x3f803f80,0x3f803f80,0x3f803f80,0x3f803f80,0x3f803f80,0x3f803f80,0x3f803f80,
  0x3f803f80,0x3f803f80,0x3f803f80,0x3f803f80,0x3f803f80,0x3f803f80,0x3f803f80,0x3f803f80,0x3f803f80,0x3f803f80,0x3f803f80,0x3f803f80,
  0x3f803f80,0x3f803f80,0x3f803f80,0x3f803f80,
};

__device__ __align__(128) float    g_part[16][8][2176];
__device__ __align__(128) float    g_kv[16][2176];
__device__ __align__(128) uint4    g_o[16 * 16 * 1024];
__device__ __align__(128) unsigned g_ocnt[2 * 16 * 32];
__device__ unsigned g_epoch[128];
#define GSTAMP(role, i) do {} while (0)
#define STAMP(role, i) do {} while (0)
#define PDUMP(role) do {} while (0)
#define PROF_SMEM 0

constexpr int STAGE_BYTES = 57344;
constexpr int OFF_H = 4 * 16384, OFF_VP = 9 * 16384, OFF_SPARE = 10 * 16384;
constexpr int OFF_XT = 172032, XT_STRIDE = 4112;
constexpr int OFF_BAR = 204928, OFF_EPOCH = OFF_BAR + 640, OFF_EX = OFF_BAR + 656, OFF_D = OFF_BAR + 672, OFF_SCALE = OFF_BAR + 704;
constexpr int OFF_F2F = 205824, OFF_F2I = 207872, OFF_F4 = 209920, OFF_ONES = 214016, OFF_KVB = 214016;
constexpr int OFF_STG = 219136, STG_STRIDE = 4352, SMEM_TOTAL = 232192 + PROF_SMEM;
enum { B_FULL1 = 0, B_EMPTY1 = 3, B_Q = 6, B_ODONE1 = 7, B_O1RDY = 8, B_XRAW = 10, B_XT = 11, B_KV = 12, B_Y = 13, B_PKFREE = 14, B_AFREE = 15,
       B_STG = 18, B_ODONE = 24, B_XFREE = 25, B_FULL2 = 33, B_CONS2 = 49, B_COUNT = 62 };
__host__ __device__ constexpr int bar_count(int i) {
  return i < B_EMPTY1 ? 1 : i < B_Q ? 4 : i == B_XT ? 4 : i == B_KV ? 2 : i == B_Y ? 9 : i == B_PKFREE ? 8
       : (i >= B_AFREE && i < B_STG) ? 16 : (i == B_ODONE || i == B_ODONE1) ? 8 : (i >= B_XFREE && i < B_FULL2) ? 4
       : (i >= B_CONS2 && i <= B_CONS2 + 10) ? 4 : i >= B_CONS2 ? 2 : (i >= B_FULL2 && i < B_FULL2 + 7) ? 2 : 1;
}
__host__ __device__ constexpr uint64_t bar_counts(int r) {
  uint64_t v = 0;
  for (int w = 0; w < 11; w++) v |= (uint64_t)(bar_count(1 + 11 * r + w) - 1) << (4 * w);
  return v;
}
constexpr uint64_t SLOT_A = 0x9245392453924594ull;
constexpr uint64_t SLOT_B = 0x7610876108761032ull;
constexpr int SPIN_LIMIT = 1 << 22;
#define PKV CU_TENSOR_MAP_L2_PROMOTION_L2_128B
#define BPRE B_KV
#define PFD 3
#define PD1 400
#define PD2 100
#define E1C 2
#define OSP 4
#define QPF 4
#define TSPLIT 1
#define OC0 2
#define OC1 2
#define BSPL 4
#define BPACE 400
#define NPOS 0
#define O1POS 1
#define HL1 4
#define OCH 3
#define O1D 3
#define QPOS 2
#define HOLD2 16
#define HSTART 1500
#define PACE 1050
#define OC 1

__device__ __forceinline__ uint32_t smem_u32(const void* p) { return (uint32_t)__cvta_generic_to_shared(p); }
__device__ __forceinline__ void wg_fence() { asm volatile("wgmma.fence.sync.aligned;" ::: "memory"); }
__device__ __forceinline__ void wg_commit() { asm volatile("wgmma.commit_group.sync.aligned;" ::: "memory"); }
template <int N> __device__ __forceinline__ void wg_wait() { asm volatile("wgmma.wait_group.sync.aligned %0;" ::"n"(N) : "memory"); }
template <int N> __device__ __forceinline__ void keep(float (&d)[N]) {
#pragma unroll
  for (int i = 0; i < N; i++) asm volatile("" : "+f"(d[i])::"memory");
}
__device__ __forceinline__ uint64_t mkdesc(uint32_t addr, uint32_t lbo, uint32_t sbo, uint32_t swz) {
  uint32_t lo = ((addr & 0x3FFFF) >> 4) | ((lbo >> 4) << 16), hi = (sbo >> 4) | (swz << 30);
  return ((uint64_t)hi << 32) | lo;
}
__device__ __forceinline__ void mbar_init(uint32_t bar, int cnt) { asm volatile("mbarrier.init.shared::cta.b64 [%0], %1;" ::"r"(bar), "r"(cnt)); }
__device__ __forceinline__ void mbar_expect(uint32_t bar, int bytes) { asm volatile("mbarrier.arrive.expect_tx.shared::cta.b64 _, [%0], %1;" ::"r"(bar), "r"(bytes) : "memory"); }
__device__ __forceinline__ void mbar_arrive(uint32_t bar) { asm volatile("mbarrier.arrive.shared::cta.b64 _, [%0];" ::"r"(bar) : "memory"); }
__device__ __forceinline__ void mbar_arrive_cl(uint32_t bar, uint32_t cta) {
  asm volatile("{\n.reg .b32 r;\nmapa.shared::cluster.u32 r, %0, %1;\nmbarrier.arrive.shared::cluster.b64 _, [r];\n}\n" ::"r"(bar), "r"(cta) : "memory");
}
__device__ __forceinline__ void mbar_wait(uint32_t bar, uint32_t parity) {
  asm volatile("{\n.reg .pred p;\n.reg .u32 n;\nmov.u32 n, 0;\n"
               "W_%=:\nmbarrier.try_wait.parity.shared::cta.b64 p, [%0], %1;\n@p bra D_%=;\n"
               "add.u32 n, n, 1;\nsetp.lt.u32 p, n, %2;\n@p bra W_%=;\ntrap;\nD_%=:\n}\n" ::"r"(bar), "r"(parity), "n"(SPIN_LIMIT) : "memory");
}
__device__ __forceinline__ void fence_async() { asm volatile("fence.proxy.async.shared::cta;" ::: "memory"); }
__device__ __forceinline__ void bar_sync(int id) { asm volatile("bar.sync %0, 128;" ::"r"(id) : "memory"); }
__device__ __forceinline__ void tma2d(uint32_t dst, const CUtensorMap* m, int c0, int c1, uint32_t bar) {
  asm volatile("cp.async.bulk.tensor.2d.shared::cluster.global.mbarrier::complete_tx::bytes [%0], [%1, {%3, %4}], [%2];"
               ::"r"(dst), "l"(m), "r"(bar), "r"(c0), "r"(c1) : "memory");
}
__device__ __forceinline__ void tma2d_mc(uint32_t dst, const CUtensorMap* m, int c0, int c1, uint32_t bar) {
  asm volatile("cp.async.bulk.tensor.2d.shared::cluster.global.mbarrier::complete_tx::bytes.multicast::cluster [%0], [%1, {%3, %4}], [%2], %5;"
               ::"r"(dst), "l"(m), "r"(bar), "r"(c0), "r"(c1), "h"((uint16_t)3) : "memory");
}
__device__ __forceinline__ void tma3d(uint32_t dst, const CUtensorMap* m, int c0, int c1, int c2, uint32_t bar) {
  asm volatile("cp.async.bulk.tensor.3d.shared::cluster.global.mbarrier::complete_tx::bytes [%0], [%1, {%3, %4, %5}], [%2];"
               ::"r"(dst), "l"(m), "r"(bar), "r"(c0), "r"(c1), "r"(c2) : "memory");
}
__device__ __forceinline__ void tma4d(uint32_t dst, const CUtensorMap* m, int c0, int c1, int c2, int c3, uint32_t bar) {
  asm volatile("cp.async.bulk.tensor.4d.shared::cluster.global.mbarrier::complete_tx::bytes [%0], [%1, {%3, %4, %5, %6}], [%2];"
               ::"r"(dst), "l"(m), "r"(bar), "r"(c0), "r"(c1), "r"(c2), "r"(c3) : "memory");
}
__device__ __forceinline__ void bulk_ld(uint32_t dst, const void* src, int bytes, uint32_t bar) {
  asm volatile("cp.async.bulk.shared::cluster.global.mbarrier::complete_tx::bytes [%0], [%1], %2, [%3];" ::"r"(dst), "l"(src), "r"(bytes), "r"(bar) : "memory");
}
__device__ __forceinline__ void bulk_ld_mc(uint32_t dst, const void* src, int bytes, uint32_t bar) {
  asm volatile("cp.async.bulk.shared::cluster.global.mbarrier::complete_tx::bytes.multicast::cluster [%0], [%1], %2, [%3], %4;"
               ::"r"(dst), "l"(src), "r"(bytes), "r"(bar), "h"((uint16_t)3) : "memory");
}
__device__ __forceinline__ void tma2d_st(const CUtensorMap* m, uint32_t src, int c0, int c1) {
  asm volatile("cp.async.bulk.tensor.2d.global.shared::cta.bulk_group [%0, {%2, %3}], [%1];" ::"l"(m), "r"(src), "r"(c0), "r"(c1) : "memory");
}
__device__ __forceinline__ void pf_l2(const void* p, int bytes) { asm volatile("cp.async.bulk.prefetch.L2.global [%0], %1;" ::"l"(p), "r"(bytes) : "memory"); }
__device__ __forceinline__ void pf_t2d(const CUtensorMap* m, int c0, int c1) {
  asm volatile("cp.async.bulk.prefetch.tensor.2d.L2.global [%0, {%1, %2}];" ::"l"(m), "r"(c0), "r"(c1) : "memory");
}
__device__ __forceinline__ void pf_t3d(const CUtensorMap* m, int c0, int c1, int c2) {
  asm volatile("cp.async.bulk.prefetch.tensor.3d.L2.global [%0, {%1, %2, %3}];" ::"l"(m), "r"(c0), "r"(c1), "r"(c2) : "memory");
}
__device__ __forceinline__ void ldsm4(uint32_t (&r)[4], uint32_t a) {
  asm volatile("ldmatrix.sync.aligned.m8n8.x4.shared.b16 {%0,%1,%2,%3}, [%4];" : "=r"(r[0]), "=r"(r[1]), "=r"(r[2]), "=r"(r[3]) : "r"(a) : "memory");
}
__device__ __forceinline__ void ldsm4t(uint32_t (&r)[4], uint32_t a) {
  asm volatile("ldmatrix.sync.aligned.m8n8.x4.trans.shared.b16 {%0,%1,%2,%3}, [%4];" : "=r"(r[0]), "=r"(r[1]), "=r"(r[2]), "=r"(r[3]) : "r"(a) : "memory");
}
__device__ __forceinline__ void stsm4(uint32_t a, uint32_t r0, uint32_t r1, uint32_t r2, uint32_t r3) {
  asm volatile("stmatrix.sync.aligned.m8n8.x4.shared.b16 [%0], {%1,%2,%3,%4};" ::"r"(a), "r"(r0), "r"(r1), "r"(r2), "r"(r3) : "memory");
}
__device__ __forceinline__ uint32_t pk2(float lo, float hi) { uint32_t r; asm("cvt.rn.bf16x2.f32 %0, %1, %2;" : "=r"(r) : "f"(hi), "f"(lo)); return r; }
__device__ __forceinline__ uint32_t hmul(uint32_t a, uint32_t b) { uint32_t r; asm("mul.rn.bf16x2 %0, %1, %2;" : "=r"(r) : "r"(a), "r"(b)); return r; }
__device__ __forceinline__ uint32_t hadd(uint32_t a, uint32_t b) { uint32_t r; asm("add.rn.bf16x2 %0, %1, %2;" : "=r"(r) : "r"(a), "r"(b)); return r; }
__device__ __forceinline__ uint32_t hmax(uint32_t a, uint32_t b) { uint32_t r; asm("max.bf16x2 %0, %1, %2;" : "=r"(r) : "r"(a), "r"(b)); return r; }
__device__ __forceinline__ uint32_t hmin(uint32_t a, uint32_t b) { uint32_t r; asm("min.bf16x2 %0, %1, %2;" : "=r"(r) : "r"(a), "r"(b)); return r; }
__device__ __forceinline__ uint32_t hmaxabs(uint32_t a, uint32_t b) { uint32_t r; asm("max.xorsign.abs.bf16x2 %0, %1, %2;" : "=r"(r) : "r"(a), "r"(b)); return r; }
__device__ __forceinline__ float ex2(float x) { float r; asm("ex2.approx.ftz.f32 %0, %1;" : "=f"(r) : "f"(x)); return r; }
__device__ __forceinline__ float rcp_fast(float x) { float r; asm("rcp.approx.ftz.f32 %0, %1;" : "=f"(r) : "f"(x)); return r; }
__device__ __forceinline__ uint32_t phi2(float lo, float hi) {
  uint32_t t;
  asm("cvt.rn.relu.bf16x2.f32 %0, %1, %2;" : "=r"(t) : "f"(hi), "f"(lo));
  const uint32_t e = pk2(ex2(lo * 1.4426950408889634f), ex2(hi * 1.4426950408889634f));
  return hadd(hadd(t, hmin(e, 0x3F803F80u)), 0x35863586u);
}
__device__ __forceinline__ bool opaque_true() { uint32_t v; asm volatile("mov.u32 %0, %%nctaid.y;" : "=r"(v)); return v != 0; }
__device__ __forceinline__ int normalise(uint32_t (&v)[32], float fd) {
  const float f0 = fd + __uint_as_float(v[0] << 16);
  uint32_t m[4] = {hmaxabs(__float_as_uint(f0) >> 16, v[0]), v[1], v[2], v[3]};
#pragma unroll
  for (int i = 4; i < 32; i++) m[i & 3] = hmaxabs(m[i & 3], v[i]);
  m[0] = hmaxabs(hmaxabs(m[0], m[1]), hmaxabs(m[2], m[3]));
  const int e = min(max((int)(__reduce_max_sync(~0u, max(m[0] & 0x7FFFu, (m[0] >> 16) & 0x7FFFu)) >> 7), 1), 253);
  if (e > 141) {
#pragma unroll
    for (int i = 0; i < 32; i++) v[i] = hmul(v[i], 0x07000700u);
  }
  const uint32_t sc = (e > 141 ? 255 - e : 142 - e) * 0x00800080u;
#pragma unroll
  for (int i = 0; i < 32; i++) {
    const uint32_t a = hmul(v[i], sc);
    v[i] = (a & 0x0FFF0FFFu) * 7 + a;
  }
  v[0] = __byte_perm(v[0], __half_as_ushort(__float2half_rn(f0 * __uint_as_float((254 - e) << 23))), 0x3254);
  return e;
}
__device__ __forceinline__ void poll_ge(const unsigned* p, unsigned target) {
#pragma unroll 1
  for (int n = 0; n < SPIN_LIMIT; n++) {
    unsigned v;
    asm volatile("ld.relaxed.gpu.global.u32 %0, [%1];" : "=r"(v) : "l"(p) : "memory");
    if (__all_sync(~0u, (int)(v - target) >= 0)) { asm volatile("fence.acquire.gpu;" ::: "memory"); return; }
  }
  __trap();
}

__device__ __forceinline__ bool elect_one() {
  uint32_t p;
  asm volatile("{\n.reg .pred p;\nelect.sync _|p, 0xffffffff;\nselp.u32 %0, 1, 0, p;\n}\n" : "=r"(p));
  return p;
}
__device__ __forceinline__ uint4 ld_nc4(const void* p) {
  uint4 v;
  asm volatile("ld.global.nc.L1::no_allocate.v4.u32 {%0,%1,%2,%3}, [%4];" : "=r"(v.x), "=r"(v.y), "=r"(v.z), "=r"(v.w) : "l"(p));
  return v;
}
__device__ __forceinline__ void st_cg4(void* p, uint4 v) {
  asm volatile("st.global.cg.v4.u32 [%0], {%1,%2,%3,%4};" ::"l"(p), "r"(v.x), "r"(v.y), "r"(v.z), "r"(v.w) : "memory");
}
__device__ __forceinline__ uint32_t mapa(uint32_t a, uint32_t cta) { uint32_t r; asm("mapa.shared::cluster.u32 %0, %1, %2;" : "=r"(r) : "r"(a), "r"(cta)); return r; }
__device__ __forceinline__ void st_async(uint32_t a, uint32_t v, uint32_t bar) {
  asm volatile("st.async.weak.shared::cluster.mbarrier::complete_tx::bytes.b32 [%0], %1, [%2];" ::"r"(a), "r"(v), "r"(bar) : "memory");
}
__device__ __forceinline__ void st_async4(uint32_t a, uint32_t x, uint32_t y, uint32_t z, uint32_t w, uint32_t bar) {
  asm volatile("st.async.weak.shared::cluster.mbarrier::complete_tx::bytes.v4.b32 [%0], {%1,%2,%3,%4}, [%5];" ::"r"(a), "r"(x), "r"(y), "r"(z), "r"(w), "r"(bar) : "memory");
}
__device__ __forceinline__ void tma3d_st(const CUtensorMap* m, uint32_t src, int c0, int c1, int c2) {
  asm volatile("cp.async.bulk.tensor.3d.global.shared::cta.bulk_group [%0, {%2, %3, %4}], [%1];" ::"l"(m), "r"(src), "r"(c0), "r"(c1), "r"(c2) : "memory");
}
__device__ __forceinline__ uint4 ld_rlx4(const void* p) {
  uint4 v;
  asm volatile("{\n.reg .b128 t;\n.reg .b64 a, b;\nld.relaxed.gpu.global.b128 t, [%4];\nmov.b128 {a, b}, t;\nmov.b64 {%0, %1}, a;\nmov.b64 {%2, %3}, b;\n}\n"
               : "=r"(v.x), "=r"(v.y), "=r"(v.z), "=r"(v.w) : "l"(p) : "memory");
  return v;
}
__device__ __forceinline__ void ld_stale4(uint4& v, const void* p, uint32_t tag) {
  asm volatile("{\n.reg .b128 t;\n.reg .b64 a, b;\n.reg .b32 x;\n.reg .pred p;\n"
               "lop3.b32 x, %0, %5, 1, 0x28;\nsetp.ne.u32 p, x, 0;\n"
               "mov.b64 a, {%0, %1};\nmov.b64 b, {%2, %3};\nmov.b128 t, {a, b};\n"
               "@p ld.relaxed.gpu.global.b128 t, [%4];\n"
               "mov.b128 {a, b}, t;\nmov.b64 {%0, %1}, a;\nmov.b64 {%2, %3}, b;\n}\n"
               : "+r"(v.x), "+r"(v.y), "+r"(v.z), "+r"(v.w) : "l"(p), "r"(tag) : "memory");
}
__device__ __forceinline__ void st_tag4(void* p, float a, float b, float c, float d, uint32_t tag) {
  asm volatile("{\n.reg .b128 t;\n.reg .b64 a, b;\nmov.b64 a, {%1, %2};\nmov.b64 b, {%3, %4};\nmov.b128 t, {a, b};\nst.relaxed.gpu.global.b128 [%0], t;\n}\n"
               ::"l"(p), "r"((__float_as_uint(a) & ~1u) | tag), "f"(b), "f"(c), "f"(d) : "memory");
}
__device__ __forceinline__ uint32_t stale8(const uint4 (&f)[8], uint32_t tag) {
  uint32_t r[4];
#pragma unroll
  for (int i = 0; i < 4; i++) asm("lop3.b32 %0, %1, %2, %3, 0x7E;" : "=r"(r[i]) : "r"(f[2 * i].x), "r"(f[2 * i + 1].x), "r"(tag));
  asm("lop3.b32 %0, %0, %1, %2, 0xFE;" : "+r"(r[0]) : "r"(r[1]), "r"(r[2]));
  return r[0] | r[3];
}

struct ConvC { uint32_t a1[2][4], wa[2], wb[2], sg; };
__device__ __forceinline__ uint64_t dsc(uint32_t lo, uint32_t hi) { return ((uint64_t)hi << 32) | lo; }
__device__ __forceinline__ uint32_t hfma(uint32_t a, uint32_t b, uint32_t c) { uint32_t r; asm("fma.rn.f16x2 %0, %1, %2, %3;" : "=r"(r) : "r"(a), "r"(b), "r"(c)); return r; }
__device__ __forceinline__ uint32_t hfnma(uint32_t a, uint32_t b, uint32_t c) { uint32_t r; asm("{.reg .b32 n; neg.f16x2 n, %1; fma.rn.f16x2 %0, n, %2, %3;}" : "=r"(r) : "r"(a), "r"(b), "r"(c)); return r; }
__device__ __forceinline__ uint32_t hmul16(uint32_t a, uint32_t b) { uint32_t r; asm("mul.rn.f16x2 %0, %1, %2;" : "=r"(r) : "r"(a), "r"(b)); return r; }
template <int N> __device__ __forceinline__ void keepu(uint32_t (&d)[N]) {
#pragma unroll
  for (int i = 0; i < N; i++) asm volatile("" : "+r"(d[i])::"memory");
}
__device__ __forceinline__ void conv_m1(const ConvC& K, uint32_t (&u)[16], uint32_t l) {
  wg_fence();
  wgmma_hrs_n64<1>(u, K.a1[0][0], K.a1[0][1], K.a1[0][2], K.a1[0][3], dsc(l, 32), 0);
  wgmma_hrs_n64<1>(u, K.a1[1][0], K.a1[1][1], K.a1[1][2], K.a1[1][3], dsc(l + 16, 32), 1);
  wg_commit();
}
__device__ __forceinline__ void conv_s2(const ConvC& K, uint32_t (&u)[16], uint32_t (&Z)[2][8], uint32_t dfl) {
  uint32_t fr[8], fi[8];
#pragma unroll
  for (int c = 0; c < 8; c++) {
    const uint32_t r = hfma(K.wa[c & 1], u[2 * c + 1], u[2 * c]);
    fi[c] = hfma(K.wb[c & 1], r, u[2 * c + 1]);
    fr[c] = hfma(K.wa[c & 1], fi[c], r);
  }
  wg_fence();
#pragma unroll
  for (int p = 0; p < 2; p++) {
    wgmma_hrs_n32<0>(Z[p], fr[4 * p], fr[4 * p + 2], fr[4 * p + 1], fr[4 * p + 3], dsc(dfl, 32), 0);
    wgmma_hrs_n32<0>(Z[p], fi[4 * p], fi[4 * p + 2], fi[4 * p + 1], fi[4 * p + 3], dsc(dfl + 16, 32), 1);
  }
  wg_commit();
}
__device__ __forceinline__ void conv_win(const ConvC& K, const uint32_t (&X)[2][8], uint32_t (&W)[2][8]) {
#pragma unroll
  for (int b = 0; b < 4; b++)
#pragma unroll
    for (int c = 0; c < 2; c++) {
      const uint32_t xr = X[b >> 1][2 * c + (b & 1)], xi = X[b >> 1][4 + 2 * c + (b & 1)];
      const int a = b ? b - 1 : 0;
      W[b >> 1][2 * c + (b & 1)] = b ? hfnma(K.sg, X[a >> 1][4 + 2 * c + (a & 1)], xr) : hmul16(xr, 0x3C003C00u);
      W[b >> 1][4 + 2 * c + (b & 1)] = b ? hfma(K.sg, X[a >> 1][2 * c + (a & 1)], xi) : hmul16(xi, 0x3C003C00u);
    }
}
template <int p>
__device__ __forceinline__ void conv_pw(uint32_t (&X)[2][8], uint32_t (&H)[2][8], uint32_t (&V)[8], uint32_t dil) {
  uint32_t pr[2][2], pi[2][2];
#pragma unroll
  for (int jj = 0; jj < 2; jj++)
#pragma unroll
    for (int c = 0; c < 2; c++) {
      const int j = 2 * p + jj;
      uint32_t sr = 0, si = 0;
#pragma unroll
      for (int a = 0; a <= j; a++) {
        const int b = j - a;
        const uint32_t hr = H[a >> 1][2 * c + (a & 1)], hi = H[a >> 1][4 + 2 * c + (a & 1)];
        const uint32_t xr = X[b >> 1][2 * c + (b & 1)], xi = X[b >> 1][4 + 2 * c + (b & 1)];
        sr = a == 0 ? hmul16(hr, xr) : hfma(hr, xr, sr);
        si = a == 0 ? hmul16(hr, xi) : hfma(hr, xi, si);
        sr = hfnma(hi, xi, sr);
        si = hfma(hi, xr, si);
      }
      pr[jj][c] = sr; pi[jj][c] = si;
    }
  wg_fence();
  wgmma_hrs_n32<0>(V, pr[0][0], pr[1][0], pr[0][1], pr[1][1], dsc(dil, 32), 0);
  wgmma_hrs_n32<0>(V, pi[0][0], pi[1][0], pi[0][1], pi[1][1], dsc(dil + 16, 32), 1);
  wg_commit();
}
template <int p>
__device__ __forceinline__ void conv_it(const ConvC& K, uint32_t (&V)[8], uint32_t vst) {
#pragma unroll
  for (int jj = 0; jj < 2; jj++) {
    uint32_t wr[2], wi[2];
#pragma unroll
    for (int c = 0; c < 2; c++) {
      const uint32_t r = hfnma(K.wa[c], V[4 + 2 * c + jj], V[2 * c + jj]);
      wi[c] = hfnma(K.wb[c], r, V[4 + 2 * c + jj]);
      wr[c] = hfnma(K.wa[c], wi[c], r);
    }
    stsm4(vst + (2 * p + jj) * 2048, wr[0], wr[1], wi[0], wi[1]);
  }
}
__device__ __forceinline__ void conv_m4(uint32_t (&y)[8], uint32_t (&a)[4][4], uint32_t d4l) {
  wg_fence();
  wgmma_hrs_n32<0>(y, a[0][0], a[0][1], a[0][2], a[0][3], dsc(d4l, 64), 0);
#pragma unroll
  for (int s = 1; s < 4; s++) wgmma_hrs_n32<0>(y, a[s][0], a[s][1], a[s][2], a[s][3], dsc(d4l + s * 16, 64), 1);
  wg_commit();
}

struct Params {
  CUtensorMap tmX, tmW, tmWo, tmWo1, tmK, tmV, tmQ, tmOA, tmOB;
  const __nv_bfloat16 *shift_k, *h, *D, *x, *w, *wo, *q;
  float *part, *kv;
  uint4* o;
  unsigned *ocnt, *epoch;
  const uint32_t *thr, *img;
};

__global__ void __cluster_dims__(2, 1, 1) __launch_bounds__(384, 1) fused_kernel(const __grid_constant__ Params P) {
  extern __shared__ __align__(1024) uint8_t smem[];
  const uint32_t sb = smem_u32(smem);
  const uint32_t bars = sb + OFF_BAR;
  const int tid = threadIdx.x, lane = tid & 31;
  const int warp = __shfl_sync(~0u, tid >> 5, 0);
  const int rank = blockIdx.x & 1, cl = blockIdx.x >> 1;
  const int mb = cl >> 3, hq = cl & 7;
  const int hp = 2 * hq + rank;
  const int rb = 2 * mb + (hq >> 2), cb = hq & 3;
#define BAR(i) (bars + 8 * (i))

  if (tid == 0) { STAMP(0, 0); GSTAMP(0, 30); }
  if (warp == 8) {
    if (elect_one()) {
      mbar_init(BAR(B_FULL1), 1);
      asm volatile("fence.mbarrier_init.release.cluster;" ::: "memory");
      mbar_expect(BAR(B_FULL1), STAGE_BYTES);
      tma3d(sb + 32768, &P.tmW, hp * 64, 0, 0, BAR(B_FULL1));
    }
    if (lane == 0) STAMP(3, 21);
  } else if (lane == 0) {
    const int wi = warp - (warp > 8);
#pragma unroll
    for (int r = 0; r < 6; r++)
      if (r < 5 || wi < B_COUNT - 56) mbar_init(BAR(1 + 11 * r + wi), ((uint32_t)(bar_counts(r) >> (4 * wi)) & 15) + 1);
    asm volatile("fence.mbarrier_init.release.cluster;" ::: "memory");
  }
  if (tid == 0) STAMP(2, 6);
  asm volatile("barrier.cluster.arrive.relaxed.aligned;\nbarrier.cluster.wait.aligned;" ::: "memory");
  if (warp == 8 && elect_one()) tma2d_mc(sb + rank * 16384, &P.tmX, 0, mb * 256 + rank * 128, BAR(B_FULL1));
  if (tid == 256) STAMP(2, 7);

  if (warp < 8) {
    asm volatile("setmaxnreg.inc.sync.aligned.u32 224;");
    const int wg = warp >> 2, w = warp & 3, g = lane >> 2, q = lane & 3, t = tid & 127;
    const bool elect = (t == 0);
    const uint32_t s16 = (sb & 0x3FFFF) >> 4;
    constexpr uint32_t SW128 = 64 | (1u << 30);
    uint32_t pq[2][16], v[32];
    int ehs;
    ConvC K;
    {
      float acc[2][96];
      int st = 0, ph = 0;
#pragma unroll 1
      for (int kb = 0; kb < 14; kb++) {
        mbar_wait(BAR(B_FULL1 + st), ph);
        if (kb == 0 && elect) { STAMP(wg, 1); GSTAMP(wg, 26); }
        if (kb == 8 && elect) { STAMP(wg, 16); GSTAMP(wg, 25); }
        if (tid == 0) STAMP(2, 8 + kb);
        const uint32_t da = s16 + st * (STAGE_BYTES >> 4) + wg * 1024 + (1 << 16);
        const uint32_t db = s16 + st * (STAGE_BYTES >> 4) + 2048 + (512 << 16);
        wg_fence();
#pragma unroll
        for (int ks = 0; ks < 4; ks++) {
          wgmma_ss_n192<0, 1>(acc[0], dsc(da + ks * 2, SW128), dsc(db + ks * 128, SW128), (kb | ks) != 0);
          wgmma_ss_n192<0, 1>(acc[1], dsc(da + 512 + ks * 2, SW128), dsc(db + ks * 128, SW128), (kb | ks) != 0);
        }
        wg_commit();
        wg_wait<1>();
        if (kb > 0 && t < 2) mbar_arrive_cl(BAR(B_EMPTY1 + (st == 0 ? 2 : st - 1)), t);
        if (++st == 3) { st = 0; ph ^= 1; }
      }
#define TAIL_MMA(mt, stage) do { wg_fence(); _Pragma("unroll") for (int ks = 0; ks < 4; ks++) \
        wgmma_ss_n192<0, 1>(acc[mt], dsc(s16 + (stage) * (STAGE_BYTES >> 4) + wg * 1024 + (mt) * 512 + (1 << 16) + ks * 2, SW128), \
                            dsc(s16 + (stage) * (STAGE_BYTES >> 4) + 2048 + (512 << 16) + ks * 128, SW128), 1); wg_commit(); } while (0)
      mbar_wait(BAR(B_FULL1 + 2), 0);
      TAIL_MMA(0, 2);
      wg_wait<1>();
      if (t < 2) mbar_arrive_cl(BAR(B_EMPTY1 + 1), t);
      mbar_wait(BAR(B_FULL1 + 0), 1);
      TAIL_MMA(0, 0);
      TAIL_MMA(1, 2);
      if (!TSPLIT) TAIL_MMA(1, 0);
      const uint32_t lrow = sb + (16 * w + 8 * ((lane >> 3) & 1) + (lane & 7)) * 128 + (((lane >> 4) ^ (lane & 7)) << 4);
      const uint32_t pko = OFF_H + wg * 8192, vo0 = 6 * 16384 + wg * 8192, vo1 = 7 * 16384 + wg * 16384;
#define E1K(mt, i) do { if (opaque_true()) { _Pragma("unroll") for (int j = (i); j < (i) + 2; j++) { \
          const float* a = &acc[mt][32 + 8 * j]; const float* b = a + 32; const uint32_t o = lrow ^ (j * 32); \
          stsm4(o + ((mt) ? vo1 : vo0), pk2(b[0], b[1]), pk2(b[2], b[3]), pk2(b[4], b[5]), pk2(b[6], b[7])); \
          stsm4(o + pko + (mt) * 16384, phi2(a[0], a[1]), phi2(a[2], a[3]), phi2(a[4], a[5]), phi2(a[6], a[7])); } } } while (0)
#define E1Q(mt) do { if (opaque_true()) { _Pragma("unroll") for (int i = 0; i < 16; i++) pq[mt][i] = phi2(acc[mt][2 * i], acc[mt][2 * i + 1]); } } while (0)
      const uint4* hp4 = (const uint4*)(P.h + (blockIdx.x * 8 + warp) * 2048) + ((lane & 15) * 2 + (lane >> 4));
#define LOAD_H(i0, i1) do { _Pragma("unroll") for (int i = (i0); i < (i1); i++) { \
        const uint4 u = ld_nc4(hp4 + i * 32); v[4 * i] = u.x; v[4 * i + 1] = u.y; v[4 * i + 2] = u.z; v[4 * i + 3] = u.w; } } while (0)
      mbar_wait(BAR(B_EMPTY1 + 1), 0);
      if (TSPLIT) wg_wait<1>(); else wg_wait<2>();
      keep(acc[0]);
      if (elect) STAMP(wg, 18);
      E1K(0, 0);
      if (TSPLIT) TAIL_MMA(1, 0);
      LOAD_H(0, HL1);
      E1K(0, 2);
      if (elect) STAMP(wg, 19);
      LOAD_H(HL1, 8);
      if (QPOS == 0) E1Q(0);
      if (elect) STAMP(wg, 20);
      {
        const uint4* ct = (const uint4*)P.thr + t;
#pragma unroll
        for (int s = 0; s < 2; s++) { const uint4 u = ld_nc4(ct + s * 128); K.a1[s][0] = u.x; K.a1[s][1] = u.y; K.a1[s][2] = u.z; K.a1[s][3] = u.w; }
        const uint4 u = ld_nc4(ct + 2 * 128);
        K.wa[0] = u.x; K.wa[1] = u.y; K.wb[0] = u.z; K.wb[1] = u.w;
        K.sg = (lane & 4) ? 0xBC00BC00u : 0x3C003C00u;
      }
      mbar_wait(BAR(B_XT), 0);
      const uint32_t tag = ~*(volatile unsigned*)(smem + OFF_EPOCH) & 1;
      wg_wait<0>();
      keep(acc[1]);
      if (t < 2) mbar_arrive_cl(BAR(B_EMPTY1 + 0), t);
      if (elect) { STAMP(wg, 2); GSTAMP(wg, 27); }
      E1K(1, 0);
      E1K(1, 2);
      fence_async();
      bar_sync(1 + wg);
      if (elect) STAMP(wg, 3);
      float kva[36];
      wg_fence();
#pragma unroll
      for (int ks = 0; ks < 8; ks++) {
        const uint32_t vb = ((ks >> 2 ? vo1 : vo0) >> 4) + (ks & 3) * 128;
        wgmma_ss_n72<1, 1>(kva, dsc(s16 + (pko >> 4) + (ks >> 2) * 1024 + (ks & 3) * 128 + (1 << 16), SW128),
                           dsc(s16 + vb + (((OFF_ONES >> 4) - vb) << 16), SW128), ks != 0);
      }
      wg_commit();
      int eh = 0;
      if (QPOS == 1) E1Q(0);
      if (NPOS == 0) eh = normalise(v, lane == 0 ? *(const float*)(smem + OFF_D + 4 * warp) : 0.f);
      wg_wait<0>();
      keep(kva);
      if (elect) STAMP(wg, 24);
      {
        float4 p[5];
#pragma unroll
        for (int c = 0; c < 4; c++)
          p[c] = w < 2 ? make_float4(kva[4 * c], kva[4 * c + 1], kva[4 * c + 2], kva[4 * c + 3])
                       : make_float4(kva[16 + 4 * c], kva[17 + 4 * c], kva[18 + 4 * c], kva[19 + 4 * c]);
        p[4] = make_float4(kva[32], kva[34], __shfl_down_sync(~0u, kva[32], 4), __shfl_down_sync(~0u, kva[34], 4));
        float4* hand = (float4*)(smem + 8 * 16384 + 8192 - (w >> 1) * 16384) + (t & 63);
        if ((w >> 1) != wg) {
#pragma unroll
          for (int c = 0; c < 5; c++) hand[c * 64] = p[c];
          asm volatile("bar.arrive %0, 128;" ::"r"(5 + (w >> 1)) : "memory");
        } else {
          float* dst = P.part + (hp * 8 + mb) * 2176;
          asm volatile("bar.sync %0, 128;" ::"r"(5 + (w >> 1)) : "memory");
#pragma unroll
          for (int c = 0; c < 5; c++) { const float4 u = hand[c * 64]; p[c].x += u.x; p[c].y += u.y; p[c].z += u.z; p[c].w += u.w; }
#pragma unroll
          for (int c = 0; c < 5; c++)
            if (c < 4 || !(lane & 7)) st_tag4(c < 4 ? dst + (c * 128 + t) * 4 : dst + 2048 + 16 * w + 2 * g, p[c].x, p[c].y, p[c].z, p[c].w, tag);
        }
        __syncwarp();
        if (lane == 0) mbar_arrive(BAR(B_PKFREE));
      }
      if (elect) STAMP(wg, 4);
      if (QPOS == 2) E1Q(0);
      E1Q(1);
      if (NPOS == 1) eh = normalise(v, lane == 0 ? *(const float*)(smem + OFF_D + 4 * warp) : 0.f);
      ehs = eh;
    }
    mbar_wait(BAR(B_PKFREE), 0);
    if (elect) STAMP(wg, 17);
    {
      const int e = ehs;
      uint8_t* dst = smem + OFF_H + (w & 2) * 8192 + wg * 8192 + (w & 1) * 4096 + (lane >> 4) * 512 + (lane & 15) * 16;
#pragma unroll
      for (int i = 0; i < 8; i++)
        *(uint4*)(dst + (i >> 1) * 1024 + (i & 1) * 256) = make_uint4(v[4 * i], v[4 * i + 1], v[4 * i + 2], v[4 * i + 3]);
      if (lane < 2) st_async(mapa(sb + OFF_SCALE + (8 * rank + warp) * 4, lane), min(max(e + smem[OFF_EX + warp] - 124, 1), 254) << 23, mapa(BAR(B_Y), lane));
      fence_async();
      bar_sync(1 + wg);
    }
    if (elect) STAMP(wg, 5);
    {
      const uint32_t dfl = s16 + (OFF_F2F >> 4) + (8 << 16), dil = s16 + (OFF_F2I >> 4) + (8 << 16), d4l = s16 + (OFF_F4 >> 4) + (8 << 16);
      const uint32_t xl = s16 + (OFF_XT >> 4) + 4 * wg * (XT_STRIDE >> 4) + (8 << 16);
      const uint32_t hl = s16 + (OFF_H >> 4) + wg * 512 + (8 << 16);
      uint32_t vst = sb + wg * 8192 + w * 512 + lane * 16, vld = sb + wg * 8192 + w * 2048 + lane * 16;
      uint32_t ya = mapa(sb + OFF_XT + 4 * wg * XT_STRIDE + (2 * rank + (w & 1)) * 1024 + lane * 16, w >> 1);
      const uint32_t ybar = mapa(BAR(B_Y), w >> 1);
      asm volatile("" : "+r"(vst), "+r"(vld), "+r"(ya));
      uint32_t ux[16], uh[16], W[2][8], V0[8], V1[8], y[8], a[4][4];
      uint4* const ot = P.o + ((2 * mb + wg) * 16 + hq) * 1024 + (16 * w + g) * 8 + ((4 * rank + q) ^ g);
#define YOUT(i) do { if ((w >> 1) == rank) { \
          asm volatile("st.shared.v4.b32 [%0], {%1,%2,%3,%4};" ::"r"(ya + (i) * XT_STRIDE), "r"(y[0]), "r"(y[2]), "r"(y[4]), "r"(y[6]) : "memory"); \
          asm volatile("st.shared.v4.b32 [%0], {%1,%2,%3,%4};" ::"r"(ya + (i) * XT_STRIDE + 512), "r"(y[1]), "r"(y[3]), "r"(y[5]), "r"(y[7]) : "memory"); \
        } else { \
          mbar_wait(BAR(B_XFREE + 4 * wg + (i)), 0); \
          st_async4(ya + (i) * XT_STRIDE, y[0], y[2], y[4], y[6], ybar); \
          st_async4(ya + (i) * XT_STRIDE + 512, y[1], y[3], y[5], y[7], ybar); } } while (0)
      auto ocalc = [&](const int hh) {
        if (hh == 0) {
          if (elect) STAMP(wg, 8);
          mbar_wait(BAR(B_KV), 0);
          if (elect) STAMP(wg, 9);
        }
        float oa[2][20];
        wg_fence();
#pragma unroll
        for (int m = 0; m < 4; m++) {
          const uint32_t* p = &pq[m & 1][8 * hh + 4 * (m >> 1)];
          wgmma_rs_n40<1>(oa[m & 1], p[0], p[1], p[2], p[3], dsc(s16 + (OFF_KVB >> 4) + hh * 160 + (m >> 1) * 16 + (8 << 16), 32), m >> 1);
        }
        wg_commit();
        wg_wait<0>();
#pragma unroll
        for (int mt = 0; mt < 2; mt++) {
          float (&o)[20] = oa[mt];
          keep(o);
          const uint32_t den = hadd(pk2(o[16], o[18]), 0x35863586u);
#pragma unroll
          for (int r = 0; r < 2; r++) {
            const float ri = rcp_fast(__uint_as_float(r ? (den & 0xFFFF0000u) : (den << 16)));
            uint4 u;
            u.x = pk2(o[2 * r] * ri, o[2 * r + 1] * ri);
            u.y = pk2(o[4 + 2 * r] * ri, o[5 + 2 * r] * ri);
            u.z = pk2(o[8 + 2 * r] * ri, o[9 + 2 * r] * ri);
            u.w = pk2(o[12 + 2 * r] * ri, o[13 + 2 * r] * ri);
            st_cg4(ot + hh * 8 * 1024 + (64 * mt + 8 * r) * 8, u);
          }
        }
        __syncwarp();
        if (lane == 0) mbar_arrive(BAR(hh ? B_ODONE1 : B_ODONE));
        if (hh == 0 && elect) STAMP(wg, 10);
      };
      uint32_t X[4][2][8], H[4][2][8];
      conv_m1(K, ux, xl);
      conv_m1(K, uh, hl);
      wg_wait<1>(); keepu(ux);
      if (lane == 0) mbar_arrive_cl(BAR(B_XFREE + 4 * wg), rank ^ 1);
      conv_s2(K, ux, X[0], dfl);
      wg_wait<1>(); keepu(uh);
      conv_s2(K, uh, H[0], dfl);
#pragma unroll
      for (int i = 0; i < 4; i++) {
        const bool nx = i < 3;
        const int n = nx ? i + 1 : i;
        const uint32_t vo = (i & 1) ? OFF_H + (i >> 1) * 16384 : OFF_VP;
        if (2 * i == OCH) ocalc(0);
        if (2 * i == OCH + O1D) ocalc(1);
        if (nx) {
          conv_m1(K, ux, xl + n * (XT_STRIDE >> 4));
          conv_m1(K, uh, hl + (n >> 1) * 1024 + (n & 1) * 256);
        }
        if (2 * i != OCH && 2 * i != OCH + O1D) { if (nx) { if (i > 0) wg_wait<3>(); else wg_wait<2>(); } else wg_wait<1>(); }
        keepu(X[i][0]); keepu(X[i][1]); keepu(H[i][0]); keepu(H[i][1]);
        conv_win(K, X[i], W);
        conv_pw<0>(W, H[i], V0, dil);
        conv_pw<1>(W, H[i], V1, dil);
        wg_wait<2>();
        if (i > 0) { keepu(y); YOUT(i - 1); }
        if (2 * i + 1 == OCH) ocalc(0);
        if (2 * i + 1 == OCH + O1D) ocalc(1);
        if (nx) {
          keepu(ux); keepu(uh);
          if (lane == 0) mbar_arrive_cl(BAR(B_XFREE + 4 * wg + n), rank ^ 1);
          conv_s2(K, ux, X[n], dfl);
          wg_wait<1>();
        } else wg_wait<0>();
        keepu(V0); keepu(V1);
        conv_it<0>(K, V0, vst + vo);
        conv_it<1>(K, V1, vst + vo);
        bar_sync(1 + wg);
#pragma unroll
        for (int s = 0; s < 4; s++) ldsm4t(a[s], vld + vo + s * 512);
        if (nx) conv_s2(K, uh, H[n], dfl);
        conv_m4(y, a, d4l);
        if (i > 0 && lane < 2) mbar_arrive_cl(BAR(B_AFREE + i - 1), lane);
        if (elect && i < 3) STAMP(wg, i < 2 ? 6 + i : 9 + i);
      }
      wg_wait<0>(); keepu(y);
      YOUT(3);
      __syncwarp();
      if (lane == 0) mbar_arrive(BAR(B_Y));
      if (elect) STAMP(wg, 12);
    }
    {
      float acc[64];
#pragma unroll 1
      for (int kb = 0; kb < 16; kb++) {
        mbar_wait(BAR(B_FULL2 + kb), 0);
        if (kb == 0 && elect) { STAMP(wg, 13); GSTAMP(wg, 28); }
        const uint32_t da = s16 + ((uint32_t)(SLOT_A >> (4 * kb)) & 15) * 1024 + wg * 512 + (1 << 16);
        const uint32_t db = s16 + ((uint32_t)(SLOT_B >> (4 * kb)) & 15) * 1024 + (512 << 16);
        if (kb == HOLD2 && wg == 0) asm volatile("bar.sync 3, 256;" ::: "memory");
        wg_fence();
#pragma unroll
        for (int ks = 0; ks < 4; ks++) wgmma_ss_n128<0, 1>(acc, dsc(da + ks * 2, SW128), dsc(db + ks * 128, SW128), (kb | ks) != 0);
        wg_commit();
        if (HOLD2 < 16 && kb == 15 && wg == 1) asm volatile("bar.arrive 3, 256;" ::: "memory");
        wg_wait<1>();
        if (kb > 0 && kb < 13 && t < 2 && (kb <= 11 || t == rank)) mbar_arrive_cl(BAR(B_CONS2 + kb - 1), t);
      }
      wg_wait<0>();
      keep(acc);
      if (elect) { STAMP(wg, 14); GSTAMP(wg, 29); }
      mbar_wait(BAR(B_CONS2 + 11), 0);
      const uint32_t stg = sb + ((uint32_t)((wg ? SLOT_A : SLOT_B) >> 44) & 15) * 16384;
      const uint32_t lrow = stg + (16 * w + 8 * ((lane >> 3) & 1) + (lane & 7)) * 128 + (((lane >> 4) ^ (lane & 7)) << 4);
#pragma unroll
      for (int cp = 0; cp < 8; cp++) {
        const float* a = &acc[8 * cp];
        stsm4((lrow ^ ((cp & 3) * 32)) + (cp >> 2) * 8192, pk2(a[0], a[1]), pk2(a[2], a[3]), pk2(a[4], a[5]), pk2(a[6], a[7]));
      }
      fence_async();
      bar_sync(1 + wg);
      if (elect) {
        const int col = 1024 + 256 * cb + 128 * rank, row = 128 * rb + 64 * wg;
        tma2d_st(&P.tmOB, stg, col, row);
        tma2d_st(&P.tmOB, stg + 8192, col + 64, row);
        asm volatile("cp.async.bulk.commit_group;\ncp.async.bulk.wait_group.read 0;" ::: "memory");
        STAMP(wg, 15); GSTAMP(wg, 31); PDUMP(wg);
      }
    }
  } else {
    asm volatile("setmaxnreg.dec.sync.aligned.u32 56;");
    if (warp == 8) {
      if (lane == 0) STAMP(3, 20);
      int st = 1, ph = 1;
      const uint8_t* pfx = (const uint8_t*)P.x + (mb * 256 + hp * 16 + (lane & 15)) * 2048;
      const uint8_t* pfw = (const uint8_t*)P.w + (mb * 8 + (lane & 7)) * 6144 + (lane >> 3) * 2048 + hp * 128;
#pragma unroll 1
      for (int kb = 1; kb < 16; kb++) {
        if (kb >= 3) mbar_wait(BAR(B_EMPTY1 + st), ph);
        const uint32_t sa = sb + st * STAGE_BYTES;
        if (elect_one()) {
          mbar_expect(BAR(B_FULL1 + st), STAGE_BYTES);
          tma2d_mc(sa + rank * 16384, &P.tmX, kb * 64, mb * 256 + rank * 128, BAR(B_FULL1 + st));
          tma3d(sa + 32768, &P.tmW, hp * 64, kb * 64, 0, BAR(B_FULL1 + st));
        }
        if (kb == 1 && lane == 0) STAMP(2, 24);
        if (PFD && kb >= 2) {
#pragma unroll 1
          for (int j = kb == 2 ? 3 : kb + PFD; j <= kb + PFD && j < 16; j++) {
            if (lane < 16) asm volatile("prefetch.global.L2 [%0];" ::"l"(pfx + j * 128));
            if (lane < 24) asm volatile("prefetch.global.L2 [%0];" ::"l"(pfw + j * (64 * 6144)));
          }
          if (kb >= QPF && kb < QPF + 8) asm volatile("prefetch.global.L2 [%0];" ::"l"((const uint8_t*)P.q + (blockIdx.x * 256 + (kb - QPF) * 32 + lane) * 128));
          if (kb >= 4)
            asm volatile("prefetch.global.L2 [%0];" ::"l"(kb < 12 ? (const uint8_t*)P.h + (blockIdx.x * 256 + (kb - 4) * 32 + lane) * 128
                                                                  : (const uint8_t*)P.wo + (blockIdx.x * 128 + (kb - 12) * 32 + lane) * 128));
        }
        if (++st == 3) { st = 0; ph ^= 1; }
      }
      if (lane == 0) STAMP(2, 1);
      const unsigned epoch = P.epoch[blockIdx.x];
#define SLOT(tab, kb) (sb + ((uint32_t)((tab) >> (4 * (kb))) & 15) * 16384)
#define LOAD_B(kb) tma4d(SLOT(SLOT_B, kb), &P.tmWo, 0, ((kb) >> 3) * 32, 2 * ((kb) & 7), 4 * cb + 2 * rank, BAR(B_FULL2 + (kb)))
#define LOAD_A(kb) bulk_ld_mc(SLOT(SLOT_A, kb) + rank * 8192, P.o + (rb * 16 + (kb)) * 1024 + rank * 512, 8192, BAR(B_FULL2 + (kb)))
      mbar_wait(BAR(B_EMPTY1 + 0), 1);
      {
        const uint32_t c0 = clock();
#pragma unroll 1
        for (int i = 0; i < 14; i++) {
          const int kb = i >> 1;
          if (i == 8) mbar_wait(BAR(B_PKFREE), 0);
          while (__any_sync(~0u, (uint32_t)clock() - c0 < i * BPACE)) __nanosleep(32);
          if (elect_one()) {
            if (!(i & 1)) mbar_expect(BAR(B_FULL2 + kb), 16384);
            tma4d(SLOT(SLOT_B, kb) + (i & 1) * 8192, &P.tmWo1, 0, 0, 2 * kb, 4 * cb + 2 * rank + (i & 1), BAR(B_FULL2 + kb));
            if (i == 0) mbar_expect(BAR(B_Q), 8192);
            if (i < 4) tma3d(sb + OFF_SPARE + 2048 * i, &P.tmQ, 16 * cl, 64 * rank + 32 * (i >> 1), 2 * ((i + 6) & 7), BAR(B_Q));
          }
        }
      }
      if (lane == 0) STAMP(2, 2);
      mbar_wait(BAR(B_AFREE), 0);
      if (elect_one()) mbar_expect(BAR(B_FULL2), 16384);
      {
        const uint32_t dst = SLOT(SLOT_A, 0) + rank * 8192;
        const uint4* src = P.o + rb * 16 * 1024 + rank * 512;
        poll_ge(&P.ocnt[rb * 32], 16 * (epoch + 1));
        asm volatile("fence.proxy.async.global;" ::: "memory");
        if (lane == 0) STAMP(2, 3);
        if (elect_one()) bulk_ld_mc(dst, src, 8192, BAR(B_FULL2));
        if (lane == 0) STAMP(3, 23);
      }
#pragma unroll 1
      for (int kb = 1; kb < 7; kb++) {
        mbar_wait(BAR(kb < 3 ? B_AFREE + kb : B_CONS2 + ((kb - 3) >> 1)), 0);
        if (elect_one()) { mbar_expect(BAR(B_FULL2 + kb), 16384); LOAD_A(kb); }
      }
#pragma unroll 1
      for (int kb = 7; kb < 16; kb++) {
        mbar_wait(BAR(B_CONS2 + kb - 5), 0);
        if (kb == 8) mbar_wait(BAR(B_O1RDY), 0);
        if (elect_one()) { mbar_expect(BAR(B_FULL2 + kb), 32768); LOAD_A(kb); LOAD_B(kb); }
      }
      if (lane == 0) { P.epoch[blockIdx.x] = epoch + 1; STAMP(2, 5); PDUMP(2); }
    } else {
      const uint32_t clk0 = clock();
      const int hw = warp - 9, g = lane >> 2, q = lane & 3;
      const unsigned epoch = P.epoch[blockIdx.x];
      const uint32_t tag = ~epoch & 1;
      const uint32_t stg = sb + OFF_STG + hw * STG_STRIDE, sbar = BAR(B_STG + 2 * hw);
      int ph = 0;
      {
        uint32_t tap[2][4];
#pragma unroll
        for (int cg = 0; cg < 2; cg++) {
          const uint2 u = __ldg((const uint2*)(P.shift_k + (16 * cl + 8 * cg + g) * 4));
          tap[cg][0] = __byte_perm(u.x, 0, 0x1010); tap[cg][1] = __byte_perm(u.x, 0, 0x3232);
          tap[cg][2] = __byte_perm(u.y, 0, 0x1010); tap[cg][3] = __byte_perm(u.y, 0, 0x3232);
        }
        if (hw == 0 && lane < 8) *(float*)(smem + OFF_D + 4 * lane) = __bfloat162float(P.D[blockIdx.x * 8 + lane]);
        if (hw == 1) asm volatile("prefetch.global.L2 [%0];" ::"l"(P.thr + (lane + 32 * (blockIdx.x & 1)) * 32));
        if (hw == 0 && elect_one()) {
          *(volatile unsigned*)(smem + OFF_EPOCH) = epoch;
          mbar_expect(BAR(B_XRAW), 16384);
          mbar_expect(BAR(B_Y), 16384 + 64);
        }
        for (int i = hw * 32 + lane; i < 528; i += 96) st_tag4(P.part + (hp * 8 + mb) * 2176 + 4 * i, 0.f, 0.f, 0.f, 0.f, tag ^ 1);
        if (hw < 2 || lane < 2) st_tag4(P.kv + hp * 2176 + (4 * (hw < 2 ? 64 * mb + 32 * hw + lane : 512 + 2 * mb + lane)), 0.f, 0.f, 0.f, 0.f, tag ^ 1);
        if (lane == 0) STAMP(3, hw);
        const uint32_t xo = sb + OFF_XT + g * XT_STRIDE + rank * 2048 + q * 4;
        const int krow = 8 + (lane & 7) - (lane >> 3);
        const uint32_t ka = stg + krow * 32 + ((krow & 4) << 2), va = stg + 2304 + lane * 32 + ((lane & 4) << 2);
        int b = 0;
#pragma unroll 1
        for (int ci = hw - 3; ci < 16; ci += 3) {
          const uint32_t bo = b ? OFF_F2F - OFF_STG : 0, bn = b ? 0 : OFF_F2F - OFF_STG;
          if (ci + 3 < 16) {
            while (__any_sync(~0u, (uint32_t)clock() - clk0 < HSTART + (ci + 3) * PACE)) __nanosleep(64);
            if (elect_one()) {
              mbar_expect(sbar + 8 * (b ^ 1), 2304 + 2048);
              tma2d(stg + bn, &P.tmK, 16 * cl, 1024 * rank + 64 * (ci + 3) - 8, sbar + 8 * (b ^ 1));
              tma2d(stg + bn + 2304, &P.tmV, 16 * cl, 1024 * rank + 64 * (ci + 3), sbar + 8 * (b ^ 1));
            }
          }
          if (ci >= 0) {
            mbar_wait(sbar + 8 * b, (ph >> b) & 1);
            ph ^= 1 << b;
#pragma unroll 1
            for (int grp = 0; grp < 2; grp++) {
#pragma unroll
              for (int cg = 0; cg < 2; cg++) {
                const uint32_t dst = mapa(xo + (ci >> 3) * 1024 + ((ci & 7) * 4 + 2 * grp) * 16, cg), xbar = mapa(BAR(B_XRAW), cg);
                uint32_t vv[4], kk[4][4];
                ldsm4t(vv, (va ^ (cg * 16)) + bo + grp * 1024);
#pragma unroll
                for (int rg = 0; rg < 4; rg++) ldsm4t(kk[rg], (ka ^ (cg * 16)) + bo + grp * 1024 + rg * 256);
#pragma unroll
                for (int rg = 0; rg < 4; rg++)
                  vv[rg] = hmul(hadd(hadd(hadd(hmul(kk[rg][3], tap[cg][3]), hmul(kk[rg][2], tap[cg][2])), hmul(kk[rg][1], tap[cg][1])), hmul(kk[rg][0], tap[cg][0])), vv[rg]);
                if (cg == rank) {
#pragma unroll
                  for (int rg = 0; rg < 4; rg++) asm volatile("st.shared.b32 [%0], %1;" ::"r"(dst + (rg & 1) * 512 + (rg >> 1) * 16), "r"(vv[rg]) : "memory");
                } else {
#pragma unroll
                  for (int rg = 0; rg < 4; rg++) st_async(dst + (rg & 1) * 512 + (rg >> 1) * 16, vv[rg], xbar);
                }
              }
            }
          }
          b ^= 1;
        }
      }
      if (lane == 0) STAMP(3, 3 + hw);
      asm volatile("bar.sync 4, 96;" ::: "memory");
      if (hw == 0 && elect_one()) { mbar_expect(BAR(B_XT), 10240); bulk_ld(sb + OFF_F2F, P.img, 10240, BAR(B_XT)); }
      mbar_wait(BAR(B_XRAW), 0);
#pragma unroll 1
      for (int c = hw; c < 8; c += 3) {
        uint4* p = (uint4*)(smem + OFF_XT + c * XT_STRIDE) + lane;
        uint32_t v[32];
#pragma unroll
        for (int i = 0; i < 8; i++) { const uint4 u = p[i * 32]; v[4 * i] = u.x; v[4 * i + 1] = u.y; v[4 * i + 2] = u.z; v[4 * i + 3] = u.w; }
        const int e = normalise(v, 0.f);
#pragma unroll
        for (int i = 0; i < 8; i++) p[i * 32] = make_uint4(v[4 * i], v[4 * i + 1], v[4 * i + 2], v[4 * i + 3]);
        if (lane == 0) smem[OFF_EX + c] = e;
        if (c < 6 && elect_one()) {
          if (c < 3) mbar_expect(sbar, 4096);
          tma3d(sb + OFF_STG + 2048 * c, &P.tmQ, 16 * cl, 64 * rank, 2 * c, sbar);
        }
      }
      fence_async();
      __syncwarp();
      if (lane == 0) { mbar_arrive(BAR(B_XT)); STAMP(3, 13 + hw); }
      mbar_wait(BAR(B_PKFREE), 0);
      if (hw == 0 && lane == 0) STAMP(3, 19);
      if (PD1) __nanosleep(PD1);
      {
        const int pi = hw < 2 ? 64 * mb + 32 * hw + lane : 512 + 2 * mb + (lane & 1);
        const float* psrc = P.part + hp * 8 * 2176 + 4 * pi;
        uint4 f[8];
#pragma unroll
        for (int p = 0; p < 8; p++) f[p] = ld_rlx4(psrc + p * 2176);
        if (!opaque_true()) __trap();
#pragma unroll 1
        for (int n = 0; __any_sync(~0u, stale8(f, tag) & 1); n++) {
#pragma unroll
          for (int p = 0; p < 8; p++) ld_stale4(f[p], psrc + p * 2176, tag);
          if (n > SPIN_LIMIT) __trap();
        }
        float s0 = 0.f, s1 = 0.f, s2 = 0.f, s3 = 0.f;
#pragma unroll
        for (int p = 0; p < 8; p++) { s0 += __uint_as_float(f[p].x); s1 += __uint_as_float(f[p].y); s2 += __uint_as_float(f[p].z); s3 += __uint_as_float(f[p].w); }
        if (hw < 2 || lane < 2) st_tag4(P.kv + hp * 2176 + (4 * pi), s0, s1, s2, s3, tag);
      }
      if (lane == 0 && hw == 0) STAMP(3, 8);
      if (hw == 2) {
        unsigned* cnt = P.ocnt + (2 * mb + lane) * 32;
#pragma unroll 1
        for (int hh = 0; hh < 2; hh++) {
          mbar_wait(BAR(hh ? B_ODONE1 : B_ODONE), 0);
          if (lane < 2) asm volatile("red.release.gpu.global.add.u32 [%0], 1;" ::"l"(cnt + hh * 512) : "memory");
          if (lane == 0) STAMP(3, hh ? 6 : 7);
        }
        poll_ge(&P.ocnt[512 + rb * 32], 16 * (epoch + 1));
        asm volatile("fence.proxy.async.global;" ::: "memory");
        if (lane == 0) { mbar_arrive(BAR(B_O1RDY)); STAMP(2, 4); }
        __syncwarp();
      } else {
        if (PD2) __nanosleep(PD2);
        const int t = hw * 32 + lane;
        uint4 f[8];
        const float* src = P.kv + hp * 2176 + (4 * t);
        const float* zsrc = P.kv + hp * 2176 + (2048 + (t & 48) + 2 * (lane & 6));
        uint4 zp = ld_rlx4(zsrc);
#pragma unroll
        for (int p = 0; p < 8; p++) f[p] = ld_rlx4(src + 4 * ((p & 3) * 128 + (p >> 2) * 64));
        if (!opaque_true()) __trap();
#pragma unroll 1
        for (int n = 0; __any_sync(~0u, (stale8(f, tag) | (zp.x ^ tag)) & 1); n++) {
          ld_stale4(zp, zsrc, tag);
#pragma unroll
          for (int p = 0; p < 8; p++) ld_stale4(f[p], src + 4 * ((p & 3) * 128 + (p >> 2) * 64), tag);
          if (n > SPIN_LIMIT) __trap();
        }
#define PK2U(a, b) pk2(__uint_as_float(a), __uint_as_float(b))
#pragma unroll
        for (int hh = 0; hh < 2; hh++) {
          const uint4* ff = &f[4 * hh];
          uint8_t* dst = smem + OFF_KVB + hh * 2560 + q * 512 + (16 * hw + g) * 16;
          *(uint4*)dst = make_uint4(PK2U(ff[0].x, ff[0].y), PK2U(ff[1].x, ff[1].y), PK2U(ff[2].x, ff[2].y), PK2U(ff[3].x, ff[3].y));
          *(uint4*)(dst + 128) = make_uint4(PK2U(ff[0].z, ff[0].w), PK2U(ff[1].z, ff[1].w), PK2U(ff[2].z, ff[2].w), PK2U(ff[3].z, ff[3].w));
        }
        const uint32_t zf = (lane & 1) ? ((lane & 8) ? zp.w : zp.z) : ((lane & 8) ? zp.y : zp.x);
        const uint32_t zz = PK2U(zf, zf);
        *(uint4*)(smem + OFF_KVB + hw * 2560 + 2048 + lane * 16) = make_uint4(zz, zz, zz, zz);
        fence_async();
        __syncwarp();
        if (lane == 0) { mbar_arrive(BAR(B_KV)); if (hw == 0) STAMP(3, 9); }
      }
#define QBUF(ci) (sb + 2048 * (ci) + ((ci) < 6 ? OFF_STG : (ci) < 10 ? OFF_SPARE - 6 * 2048 : OFF_F2F - 10 * 2048))
      mbar_wait(BAR(B_Y), 0);
      if (elect_one()) {
        mbar_expect(sbar + 8, 4096);
#pragma unroll 1
        for (int ci = hw ? hw + 9 : 12; ci < 16; ci += 3) tma3d(QBUF(ci), &P.tmQ, 16 * cl, 64 * rank + 32, 2 * (ci & 7), sbar + 8);
      }
      mbar_wait(BAR(B_Q), 0);
      {
        const float2 sc0 = *(const float2*)(smem + OFF_SCALE + 8 * q), sc1 = *(const float2*)(smem + OFF_SCALE + 32 + 8 * q);
        const uint32_t yl = sb + OFF_XT + (lane & 7) * XT_STRIDE + (lane >> 3) * 16;
#pragma unroll 1
        for (int ci = hw; ci < 16; ci += 3) {
          const uint32_t qb = QBUF(ci);
          const int b = ci >= 10;
          mbar_wait(sbar + 8 * b, (ph >> b) & 1);
#pragma unroll 1
          for (int nl = 0; nl < 2; nl++) {
            uint32_t yy[2][4], qq[2][4];
            const uint32_t qa = qb + lane * 32 + ((lane & 4) << 2) + nl * 1024;
#pragma unroll
            for (int cg = 0; cg < 2; cg++) { ldsm4t(yy[cg], yl + cg * 2048 + (2 * ci + nl) * 64); ldsm4(qq[cg], qa ^ (cg * 16)); }
#pragma unroll
            for (int cg = 0; cg < 2; cg++) {
              const float2 sc = cg ? sc1 : sc0;
#pragma unroll
              for (int m = 0; m < 4; m++) {
                const float2 f = __half22float2(*(const __half2*)&yy[cg][m]);
                qq[cg][m] = hmul(qq[cg][m], pk2(f.x * sc.x, f.y * sc.y));
              }
              stsm4(qa ^ (cg * 16), qq[cg][0], qq[cg][1], qq[cg][2], qq[cg][3]);
            }
          }
          fence_async();
          __syncwarp();
          if (elect_one()) tma3d_st(&P.tmOA, qb, 16 * cl, 64 * rank + 32 * (ci >> 3), 2 * (ci & 7));
        }
        asm volatile("cp.async.bulk.commit_group;\ncp.async.bulk.wait_group.read 0;" ::: "memory");
      }
      if (lane == 0) STAMP(3, 10 + hw);
    }
  }
}

typedef CUresult (*EncodeFn)(CUtensorMap*, CUtensorMapDataType, cuuint32_t, void*, const cuuint64_t*, const cuuint64_t*,
                             const cuuint32_t*, const cuuint32_t*, CUtensorMapInterleave, CUtensorMapSwizzle,
                             CUtensorMapL2promotion, CUtensorMapFloatOOBfill);

static void enc(EncodeFn fn, CUtensorMap* m, const void* p, int rank, const cuuint64_t* dims, const cuuint64_t* strides,
                const cuuint32_t* box, CUtensorMapSwizzle swz, CUtensorMapL2promotion promo) {
  cuuint32_t es[4] = {1, 1, 1, 1};
  fn(m, CU_TENSOR_MAP_DATA_TYPE_BFLOAT16, rank, (void*)p, dims, strides, box, es, CU_TENSOR_MAP_INTERLEAVE_NONE, swz, promo,
     CU_TENSOR_MAP_FLOAT_OOB_FILL_NONE);
}

extern "C" void kernel_launch(void* const* d_in, const int* in_sizes, int n_in, void* d_out, int out_size) {
  void* fp = nullptr;
  cudaDriverEntryPointQueryResult qr;
  cudaGetDriverEntryPoint("cuTensorMapEncodeTiled", &fp, cudaEnableDefault, &qr);
  EncodeFn fn = (EncodeFn)fp;
  Params P;
  P.shift_k = (const __nv_bfloat16*)d_in[3]; P.h = (const __nv_bfloat16*)d_in[4]; P.D = (const __nv_bfloat16*)d_in[5];
  P.q = (const __nv_bfloat16*)d_in[0];
  cudaGetSymbolAddress((void**)&P.part, g_part); cudaGetSymbolAddress((void**)&P.kv, g_kv); cudaGetSymbolAddress((void**)&P.o, g_o);
  cudaGetSymbolAddress((void**)&P.ocnt, g_ocnt); cudaGetSymbolAddress((void**)&P.epoch, g_epoch);
  cudaGetSymbolAddress((void**)&P.thr, c_thr); cudaGetSymbolAddress((void**)&P.img, c_img);
  P.x = (const __nv_bfloat16*)d_in[6]; P.w = (const __nv_bfloat16*)d_in[7]; P.wo = (const __nv_bfloat16*)d_in[8];
  const CUtensorMapSwizzle S128 = CU_TENSOR_MAP_SWIZZLE_128B, S32 = CU_TENSOR_MAP_SWIZZLE_32B;
  const CUtensorMapL2promotion P0 = CU_TENSOR_MAP_L2_PROMOTION_NONE, P128 = CU_TENSOR_MAP_L2_PROMOTION_L2_128B;
  { cuuint64_t d[2] = {1024, 2048}, s[1] = {2048}; cuuint32_t b[2] = {64, 128}; enc(fn, &P.tmX, d_in[6], 2, d, s, b, S128, P128); }
  { cuuint64_t d[3] = {1024, 1024, 3}, s[2] = {6144, 2048}; cuuint32_t b[3] = {64, 64, 3}; enc(fn, &P.tmW, d_in[7], 3, d, s, b, S128, P128); }
  { cuuint64_t d[4] = {64, 64, 16, 16}, s[3] = {2048, 131072, 128}; cuuint32_t b[4] = {64, 32, 2, 2}; enc(fn, &P.tmWo, d_in[8], 4, d, s, b, S128, P128); }
  { cuuint64_t d[4] = {64, 64, 16, 16}, s[3] = {2048, 131072, 128}; cuuint32_t b[4] = {64, 32, 2, 1}; enc(fn, &P.tmWo1, d_in[8], 4, d, s, b, S128, P128); }
  { cuuint64_t d[2] = {1024, 2048}, s[1] = {2048}; cuuint32_t b[2] = {16, 72}; enc(fn, &P.tmK, d_in[1], 2, d, s, b, S32, PKV); }
  { cuuint64_t d[2] = {1024, 2048}, s[1] = {2048}; cuuint32_t b[2] = {16, 64}; enc(fn, &P.tmV, d_in[2], 2, d, s, b, S32, PKV); }
  { cuuint64_t d[3] = {1024, 128, 16}, s[2] = {32768, 2048}; cuuint32_t b[3] = {16, 32, 2}; enc(fn, &P.tmQ, d_in[0], 3, d, s, b, S32, PKV); }
  { cuuint64_t d[3] = {1024, 128, 16}, s[2] = {65536, 4096}; cuuint32_t b[3] = {16, 32, 2}; enc(fn, &P.tmOA, d_out, 3, d, s, b, S32, P0); }
  { cuuint64_t d[2] = {2048, 2048}, s[1] = {4096}; cuuint32_t b[2] = {64, 64}; enc(fn, &P.tmOB, d_out, 2, d, s, b, S128, P0); }
  cudaFuncSetAttribute(fused_kernel, cudaFuncAttributeMaxDynamicSharedMemorySize, SMEM_TOTAL);
  fused_kernel<<<128, 384, SMEM_TOTAL>>>(P);
}
```

```cpp
#include <cuda_runtime.h>
#include <cuda_bf16.h>
#include <cuda_fp16.h>
#include <cuda.h>
#include <stdint.h>

template<int TA, int TB, int SA=1> __device__ __forceinline__ void wgmma_ss_n192(float (&d)[96], uint64_t da, uint64_t db, int scale_d) {
  asm volatile("{\n.reg .pred p;\nsetp.ne.b32 p, %98, 0;\n"
    "wgmma.mma_async.sync.aligned.m64n192k16.f32.bf16.bf16 {%0, %1, %2, %3, %4, %5, %6, %7, %8, %9, %10, %11, %12, %13, %14, %15, %16, %17, %18, %19, %20, %21, %22, %23, %24, %25, %26, %27, %28, %29, %30, %31, %32, %33, %34, %35, %36, %37, %38, %39, %40, %41, %42, %43, %44, %45, %46, %47, %48, %49, %50, %51, %52, %53, %54, %55, %56, %57, %58, %59, %60, %61, %62, %63, %64, %65, %66, %67, %68, %69, %70, %71, %72, %73, %74, %75, %76, %77, %78, %79, %80, %81, %82, %83, %84, %85, %86, %87, %88, %89, %90, %91, %92, %93, %94, %95}, %96, %97, p, %101, 1, %99, %100;\n}\n"
    : "+f"(d[0]), "+f"(d[1]), "+f"(d[2]), "+f"(d[3]), "+f"(d[4]), "+f"(d[5]), "+f"(d[6]), "+f"(d[7]), "+f"(d[8]), "+f"(d[9]), "+f"(d[10]), "+f"(d[11]), "+f"(d[12]), "+f"(d[13]), "+f"(d[14]), "+f"(d[15]), "+f"(d[16]), "+f"(d[17]), "+f"(d[18]), "+f"(d[19]), "+f"(d[20]), "+f"(d[21]), "+f"(d[22]), "+f"(d[23]), "+f"(d[24]), "+f"(d[25]), "+f"(d[26]), "+f"(d[27]), "+f"(d[28]), "+f"(d[29]), "+f"(d[30]), "+f"(d[31]), "+f"(d[32]), "+f"(d[33]), "+f"(d[34]), "+f"(d[35]), "+f"(d[36]), "+f"(d[37]), "+f"(d[38]), "+f"(d[39]), "+f"(d[40]), "+f"(d[41]), "+f"(d[42]), "+f"(d[43]), "+f"(d[44]), "+f"(d[45]), "+f"(d[46]), "+f"(d[47]), "+f"(d[48]), "+f"(d[49]), "+f"(d[50]), "+f"(d[51]), "+f"(d[52]), "+f"(d[53]), "+f"(d[54]), "+f"(d[55]), "+f"(d[56]), "+f"(d[57]), "+f"(d[58]), "+f"(d[59]), "+f"(d[60]), "+f"(d[61]), "+f"(d[62]), "+f"(d[63]), "+f"(d[64]), "+f"(d[65]), "+f"(d[66]), "+f"(d[67]), "+f"(d[68]), "+f"(d[69]), "+f"(d[70]), "+f"(d[71]), "+f"(d[72]), "+f"(d[73]), "+f"(d[74]), "+f"(d[75]), "+f"(d[76]), "+f"(d[77]), "+f"(d[78]), "+f"(d[79]), "+f"(d[80]), "+f"(d[81]), "+f"(d[82]), "+f"(d[83]), "+f"(d[84]), "+f"(d[85]), "+f"(d[86]), "+f"(d[87]), "+f"(d[88]), "+f"(d[89]), "+f"(d[90]), "+f"(d[91]), "+f"(d[92]), "+f"(d[93]), "+f"(d[94]), "+f"(d[95])
    : "l"(da), "l"(db), "r"(scale_d), "n"(TA), "n"(TB), "n"(SA));
}
template<int TA, int TB, int SA=1> __device__ __forceinline__ void wgmma_ss_n128(float (&d)[64], uint64_t da, uint64_t db, int scale_d) {
  asm volatile("{\n.reg .pred p;\nsetp.ne.b32 p, %66, 0;\n"
    "wgmma.mma_async.sync.aligned.m64n128k16.f32.bf16.bf16 {%0, %1, %2, %3, %4, %5, %6, %7, %8, %9, %10, %11, %12, %13, %14, %15, %16, %17, %18, %19, %20, %21, %22, %23, %24, %25, %26, %27, %28, %29, %30, %31, %32, %33, %34, %35, %36, %37, %38, %39, %40, %41, %42, %43, %44, %45, %46, %47, %48, %49, %50, %51, %52, %53, %54, %55, %56, %57, %58, %59, %60, %61, %62, %63}, %64, %65, p, %69, 1, %67, %68;\n}\n"
    : "+f"(d[0]), "+f"(d[1]), "+f"(d[2]), "+f"(d[3]), "+f"(d[4]), "+f"(d[5]), "+f"(d[6]), "+f"(d[7]), "+f"(d[8]), "+f"(d[9]), "+f"(d[10]), "+f"(d[11]), "+f"(d[12]), "+f"(d[13]), "+f"(d[14]), "+f"(d[15]), "+f"(d[16]), "+f"(d[17]), "+f"(d[18]), "+f"(d[19]), "+f"(d[20]), "+f"(d[21]), "+f"(d[22]), "+f"(d[23]), "+f"(d[24]), "+f"(d[25]), "+f"(d[26]), "+f"(d[27]), "+f"(d[28]), "+f"(d[29]), "+f"(d[30]), "+f"(d[31]), "+f"(d[32]), "+f"(d[33]), "+f"(d[34]), "+f"(d[35]), "+f"(d[36]), "+f"(d[37]), "+f"(d[38]), "+f"(d[39]), "+f"(d[40]), "+f"(d[41]), "+f"(d[42]), "+f"(d[43]), "+f"(d[44]), "+f"(d[45]), "+f"(d[46]), "+f"(d[47]), "+f"(d[48]), "+f"(d[49]), "+f"(d[50]), "+f"(d[51]), "+f"(d[52]), "+f"(d[53]), "+f"(d[54]), "+f"(d[55]), "+f"(d[56]), "+f"(d[57]), "+f"(d[58]), "+f"(d[59]), "+f"(d[60]), "+f"(d[61]), "+f"(d[62]), "+f"(d[63])
    : "l"(da), "l"(db), "r"(scale_d), "n"(TA), "n"(TB), "n"(SA));
}
template<int TA, int TB, int SA=1> __device__ __forceinline__ void wgmma_ss_n72(float (&d)[36], uint64_t da, uint64_t db, int scale_d) {
  asm volatile("{\n.reg .pred p;\nsetp.ne.b32 p, %38, 0;\n"
    "wgmma.mma_async.sync.aligned.m64n72k16.f32.bf16.bf16 {%0, %1, %2, %3, %4, %5, %6, %7, %8, %9, %10, %11, %12, %13, %14, %15, %16, %17, %18, %19, %20, %21, %22, %23, %24, %25, %26, %27, %28, %29, %30, %31, %32, %33, %34, %35}, %36, %37, p, %41, 1, %39, %40;\n}\n"
    : "+f"(d[0]), "+f"(d[1]), "+f"(d[2]), "+f"(d[3]), "+f"(d[4]), "+f"(d[5]), "+f"(d[6]), "+f"(d[7]), "+f"(d[8]), "+f"(d[9]), "+f"(d[10]), "+f"(d[11]), "+f"(d[12]), "+f"(d[13]), "+f"(d[14]), "+f"(d[15]), "+f"(d[16]), "+f"(d[17]), "+f"(d[18]), "+f"(d[19]), "+f"(d[20]), "+f"(d[21]), "+f"(d[22]), "+f"(d[23]), "+f"(d[24]), "+f"(d[25]), "+f"(d[26]), "+f"(d[27]), "+f"(d[28]), "+f"(d[29]), "+f"(d[30]), "+f"(d[31]), "+f"(d[32]), "+f"(d[33]), "+f"(d[34]), "+f"(d[35])
    : "l"(da), "l"(db), "r"(scale_d), "n"(TA), "n"(TB), "n"(SA));
}
template<int TB, int SA=1> __device__ __forceinline__ void wgmma_rs_n40(float (&d)[20], uint32_t a0, uint32_t a1, uint32_t a2, uint32_t a3, uint64_t db, int scale_d) {
  asm volatile("{\n.reg .pred p;\nsetp.ne.b32 p, %25, 0;\n"
    "wgmma.mma_async.sync.aligned.m64n40k16.f32.bf16.bf16 {%0, %1, %2, %3, %4, %5, %6, %7, %8, %9, %10, %11, %12, %13, %14, %15, %16, %17, %18, %19}, {%20, %21, %22, %23}, %24, p, %27, 1, %26;\n}\n"
    : "+f"(d[0]), "+f"(d[1]), "+f"(d[2]), "+f"(d[3]), "+f"(d[4]), "+f"(d[5]), "+f"(d[6]), "+f"(d[7]), "+f"(d[8]), "+f"(d[9]), "+f"(d[10]), "+f"(d[11]), "+f"(d[12]), "+f"(d[13]), "+f"(d[14]), "+f"(d[15]), "+f"(d[16]), "+f"(d[17]), "+f"(d[18]), "+f"(d[19])
    : "r"(a0), "r"(a1), "r"(a2), "r"(a3), "l"(db), "r"(scale_d), "n"(TB), "n"(SA));
}
template<int TB> __device__ __forceinline__ void wgmma_hrs_n64(uint32_t (&d)[16], uint32_t a0, uint32_t a1, uint32_t a2, uint32_t a3, uint64_t db, int scale_d) {
  asm volatile("{\n.reg .pred p;\nsetp.ne.b32 p, %21, 0;\n"
    "wgmma.mma_async.sync.aligned.m64n64k16.f16.f16.f16 {%0, %1, %2, %3, %4, %5, %6, %7, %8, %9, %10, %11, %12, %13, %14, %15}, {%16, %17, %18, %19}, %20, p, 1, 1, %22;\n}\n"
    : "+r"(d[0]), "+r"(d[1]), "+r"(d[2]), "+r"(d[3]), "+r"(d[4]), "+r"(d[5]), "+r"(d[6]), "+r"(d[7]), "+r"(d[8]), "+r"(d[9]), "+r"(d[10]), "+r"(d[11]), "+r"(d[12]), "+r"(d[13]), "+r"(d[14]), "+r"(d[15])
    : "r"(a0), "r"(a1), "r"(a2), "r"(a3), "l"(db), "r"(scale_d), "n"(TB));
}
template<int TB> __device__ __forceinline__ void wgmma_hrs_n32(uint32_t (&d)[8], uint32_t a0, uint32_t a1, uint32_t a2, uint32_t a3, uint64_t db, int scale_d) {
  asm volatile("{\n.reg .pred p;\nsetp.ne.b32 p, %13, 0;\n"
    "wgmma.mma_async.sync.aligned.m64n32k16.f16.f16.f16 {%0, %1, %2, %3, %4, %5, %6, %7}, {%8, %9, %10, %11}, %12, p, 1, 1, %14;\n}\n"
    : "+r"(d[0]), "+r"(d[1]), "+r"(d[2]), "+r"(d[3]), "+r"(d[4]), "+r"(d[5]), "+r"(d[6]), "+r"(d[7])
    : "r"(a0), "r"(a1), "r"(a2), "r"(a3), "l"(db), "r"(scale_d), "n"(TB));
}

__device__ __align__(128) const uint32_t c_thr[1536] = {
  0x33fb33ff,0xa49c9de4,0x33273352,0xaf2cae76,0x33e233f1,0xa96ca7bd,0x32c432f7,0xb045afdd,0x33b733cf,0xac3eaaf7,0x3250328c,0xb0eab099,
  0x3378339a,0xadbcacff,0x31cd3211,0xb182b137,0x33d033fb,0xaadea46a,0x299e2d17,0xb3e0b396,0x32fb337a,0xafd2adb1,0xa78b1f76,0xb3f2b3ff,
  0x318b3254,0xb1c5b0e5,0xae6bac32,0xb354b3b8,0x2f4230a3,0xb321b285,0xb133b040,0xb215b2c7,0x337c33f2,0xada5a759,0xb179afc8,0xb1d6b2fe,
  0x31463293,0xb204b08e,0xb394b2ba,0xad23b055,0x2b402f4e,0xb3cbb31e,0xb3e4b3f9,0x293ba533,0xac269c52,0xb3bab400,0xb258b357,0x30e02e5f,
  0x330133e5,0xafbda922,0xb3f3b3c9,0x2727ab59,0x2deb314a,0xb36fb200,0xb194b32f,0x31bc2f0a,0xacdb2084,0xb39fb3ff,0xa565aea4,0x33f93347,
  0xb2b6b0db,0xb05ab25c,0x30892c1a,0x329733bc,0x326033d4,0xb0d6aa94,0xb00ab29b,0x32e83084,0x20e82f64,0xb3feb318,0x2d8da597,0x338133f8,
  0xb1fcae48,0xb14fb35c,0x339031b8,0x2d3a3199,0xb3e6b3ae,0x2909ac7b,0x32d133f4,0xb030a6f5,0x319d33bf,0xb1b3ac02,0x2e3ca874,0x335e33ec,
  0xacc32b89,0xb3a3b3c6,0x33f83276,0x25c930b7,0xb3dcb1f8,0xaa01b154,0x30653335,0xb2b0aef4,0xb107b383,0x32392d81,0xafa6214d,0xb307b3fe,
  0x30bc33a5,0xb273acb7,0x33c5311b,0x2ba23229,0xb0cc94b6,0xb267b400,0x30153360,0xb2e1ae31,0xb385b3ab,0x2d76ac93,0xb166a691,0xb1e7b3f5,
  0x22deb06a,0x33fd32ac,0xb337b3da,0x2ee8aa19,0x2f853387,0xb310ad6a,0x322d33fe,0xb1162216,0xb2a9abd3,0xb06fb3c2,0xb07428a6,0xb2a5b3ea,
  0xb111b3e9,0x323128be,0xb30db3c3,0x2f90abba,0x31aa227a,0x31a633fd,0x2e25ad5e,0x33633389,0x2d6a3365,0xb387ae1a,0xa21631aa,0xb3feb1a6,
  0xb3c2af85,0xabd3b310,0xb3eab22d,0x28a6b116,0xa8beb2a9,0x33e9306f,0x2bbab074,0x33c332a5,0x33fd3111,0x227a3231,0x3389330d,0xad5e2f90,
  0x2a63333f,0xb3d7aec6,0xb2a2a1b1,0xb07ab3fe,0xb3f7b158,0x25fbb1f4,0xacb7b38b,0x33a52d52,0x2e0eb025,0x336832d8,0x340030bc,0x14b63273,
  0x323533c0,0xb10c2beb,0xac9330cc,0xb3abb267,0x23433316,0xb3fdaf6f,0xb38eb225,0x2d46b11f,0xb342b29e,0x2ebbb07f,0x31e3aa7c,0x316b33d6,
  0x3264a6c3,0x30d133f5,0x2c0233ac,0xb3bfac87,0x28f0336a,0xb3e7ae02,0xb3c6b19d,0x2b89b1b3,0xa59732e8,0xb3f8b00a,0xaccfb3ed,0x33a1285b,
  0xb1b8b381,0x3199ad8d,0x336c31df,0xadf73170,0x33f42d3a,0x26f53390,0xb30423a7,0xafb2b3fc,0xb05f3030,0xb2b3b2d1,0x29e8b27a,0x33dd30b2,
  0xab5932b6,0xb3c9b05a,0x30adb089,0x327e3297,0xaf0ab3f3,0x332fa727,0x240633b0,0xb3fcac6f,0x33473194,0xaea431bc,0xb174b359,0x31daae54,
  0xb3bca565,0xac1ab3f9,0x33ee2f59,0xa842331b,0xaddf3281,0xb371b0a8,0x34002b40,0x1c5233cb,0xa759b3ef,0x33f22829,0xb2fe2c26,0xafc8b3ba,
  0x308e337c,0xb2932da5,0x3055b179,0x32ba31d6,0xb31eb146,0x2f4eb204,0xa5333394,0xb3f9ad23,0xaff33249,0xb2f1b0f3,0x30e532fb,0xb2542fd2,
  0x2b28b373,0x33cc2dd4,0xb285b18b,0x30a3b1c5,0x246a33fa,0xb3fba500,0x33962f42,0xad173321,0xadb1b3d0,0x337aaade,0xb3ffa99e,0x1f76b3e0,
  0xb0ee320d,0xb24db13c,0xac4b3398,0xb3b5ad0b,0x304ab289,0x32c1309e,0x2985b3ce,0x33e12b0f,0xaf3732f4,0xb324afe8,0xa4ce33f0,0xb3faa7ef,
  0x2dc8b34f,0x33762e82,0x9de4b3ff,0x33ff1ead,0xb1c931cd,0xb186b182,0xb3762e82,0xadc8b34f,0x324db13c,0x30ee320d,0x33b5ad0b,0x2c4b3398,
  0xb2c1309e,0xb04ab289,0xb3e12b0f,0xa985b3ce,0x3324afe8,0x2f3732f4,0x33faa7ef,0x24ce33f0,0xb285318b,0xb0a3b1c5,0xb2c7ae6b,0x3040b354,
  0x3396af42,0x2d173321,0x31413133,0xb2093215,0xb3ff299e,0x9f76b3e0,0xae8db2bd,0x334cb050,0x33b8278b,0xac3233f2,0x281033b3,0xb3ef2c57,
  0xb31e3146,0xaf4eb204,0xa533b394,0x33f9ad23,0x3400ab40,0x9c5233cb,0xae5f33e4,0xb357a93b,0xb2feac26,0x2fc8b3ba,0x3245b258,0x30f830e0,
  0x30553179,0xb2ba31d6,0xb3df2e99,0xa9b6b34a,0xb39230fd,0xad2fb241,0x3200b301,0x314a2fbd,0x337f1b11,0xad993400,0xb3ff2deb,0xa084b36f,
  0xb005b129,0x32ebb21d,0x325c2cdb,0xb0db339f,0xa92233de,0xb3e529cf,0xab59b2b6,0x33c9b05a,0xb3dd30b2,0xa9e8b27a,0x33d4ab71,0xaa9433c8,
  0x32212c0e,0xb12433bd,0xaf64b0d6,0x3318b260,0x197fb345,0x3400aeaf,0xae4833fe,0xb35c20e8,0xb23d3332,0xb102aeff,0x33aeb14f,0x2c7b31fc,
  0xb3fe3065,0xa14db2b0,0x2ebb307f,0xb342329e,0x300f2fa6,0xb2e53307,0x30d1b3f5,0x326426c3,0x302ab400,0x32d517db,0xb3e72e02,0x28f0b36a,
  0xb3fd2f6f,0x2343b316,0x2d46311f,0xb38e3225,0xb3f53015,0x2691b2e1,0xaf9b33eb,0xb30a288d,0x2a193166,0xb3da31e7,0x33d7aec6,0xaa63333f,
  0x3313b337,0x2f7a2ee8,0xa5fbb1f4,0x33f7b158,0xb1a1a8d7,0x31afb3e8,0xb36832d8,0xae0eb025,0xb3c22f85,0x2bd3b310,0xb3ea322d,0xa8a6b116,
  0xa8be32a9,0xb3e9306f,0x2bba3074,0xb3c332a5,0x33fdb111,0xa27a3231,0x3389b30d,0x2d5e2f90,0xa216b1aa,0x33feb1a6,0xaed2ae25,0x333db363,
  0xb3652edd,0x2e1ab33a,0xb1aa227a,0x31a6b3fd,0xaf853387,0xb3102d6a,0xb22d33fe,0xb116a216,0x32a9abd3,0xb06f33c2,0x307428a6,0xb2a533ea,
  0x3111b3e9,0x3231a8be,0x330db3c3,0x2f902bba,0xb2e12e31,0x3015b360,0x288db1a1,0x33ebb1af,0xb1e733f5,0xb1662691,0xb33f2f9b,0x2ec6b30a,
  0x2ee82a19,0xb33733da,0xb15833d7,0xb1f42a63,0x33e8b313,0x28d72f7a,0x302525fb,0xb2d833f7,0xb2392d81,0x3107b383,0x3307b3fe,0x2fa6214d,
  0xb35e33ec,0xae3ca874,0x97dbb00f,0x3400b2e5,0xa5c930b7,0xb3f83276,0xb316302a,0x2f6fb2d5,0x32b0aef4,0xb0653335,0xb29e33fd,0xb07f2343,
  0xb1702ccf,0x31dfb3a1,0x3345b124,0xaeaf3221,0xb3fc336c,0xa3a7adf7,0x3332b400,0x2eff997f,0xb0b23304,0xb27a2fb2,0x2b71b102,0x33c8b23d,
  0x2c0e29e8,0xb3bd33dd,0xb0d62a94,0x3260b3d4,0xb0892c1a,0x3297b3bc,0x2aad2842,0xb3d333ee,0xb3b0327e,0x2c6fb0ad,0x3241b035,0xb0fd32ce,
  0xb35933fc,0xae542406,0x3400b392,0x1b112d2f,0xaf5931da,0xb31b3174,0x321db37f,0x3129ad99,0xaf152ac6,0x332cb3d2,0xb1463293,0xb204308e,
  0xb281312e,0x30a8b219,0xab402f4e,0xb3cb331e,0xb3ef3371,0x2829addf,0x2c269c52,0xb3ba3400,0xb37c33f2,0xada52759,0x3179afc8,0xb1d632fe,
  0xacf32953,0x339cb3e3,0xb3fa33cc,0x2500ab28,0xb0942f21,0x3290b32a,0xb3d033fb,0xaade246a,0xb249317d,0x30f3b1d2,0xb2fb337a,0xafd22db1,
  0xb37332f1,0x2dd4aff3,0xb18b3254,0xb1c530e5,0xa96c27bd,0x33e2b3f1,0xb0452fdd,0x32c4b2f7,0xac3e2af7,0x33b7b3cf,0xb0ea3099,0x3250b28c,
  0xadbc2cff,0x3378b39a,0xb1823137,0x31cdb211,0xaf2c2e76,0x3327b352,0xb20d31c9,0x313cb186,0x313c3186,0xb20db1c9,0x2d0b2dc8,0xb398b376,
  0x309e30ee,0xb289b24d,0x2b0f2c4b,0xb3ceb3b5,0x2fe8304a,0xb2f4b2c1,0x27ef2985,0xb3f0b3e1,0x2e822f37,0xb34fb324,0x1ead24ce,0xb3ffb3fa,
  0xb2bdb209,0xb050b141,0xb290b32a,0x30942f21,0xb3b3b34c,0xac57ae8d,0xb0f3b1d2,0x3249317d,0xb400b3ef,0x1d1ba810,0xadd4aff3,0x337332f1,
  0xb39cb3e3,0x2cf32953,0xa500ab28,0x33fa33cc,0xae99b0f8,0x334a3245,0x33ff33b2,0x201f2c63,0x2438a9b6,0x33fc33df,0x332c33d2,0xaf15aac6,
  0x303a2ce7,0x32cb339e,0x30a83219,0xb281b12e,0x32ee31c0,0x2ffe3190,0x28292ddf,0xb3efb371,0x33b0327e,0x2c6f30ad,0xb241b035,0xb0fdb2ce,
  0x335933fc,0xae54a406,0xb400b392,0x1b11ad2f,0x2f5931da,0xb31bb174,0xb21db37f,0x31292d99,0xaaad2842,0xb3d3b3ee,0xa9cfb005,0x33de32eb,
  0x285b305f,0xb3edb2b3,0x2c0ea9e8,0x33bd33dd,0xb170accf,0xb1dfb3a1,0x33453124,0x2eaf3221,0xb3fcb36c,0x23a7adf7,0x33323400,0xaeff997f,
  0xb0b2b304,0x327a2fb2,0x2b713102,0xb3c8b23d,0xb400b2e5,0x17dbb00f,0x2e023264,0xb36ab0d1,0xaf6fb2d5,0x3316302a,0xb11fa8f0,0xb225b3e7,
  0x307f2343,0x329e33fd,0xb3d6b38e,0x2a7cad46,0x33f53342,0xa6c32ebb,0xac87b1e3,0x33ac316b,0x28d7af7a,0x33e83313,0xb2d8b3f7,0x3025a5fb,
  0x33eb31af,0x288d31a1,0x2bebae0e,0x33c03368,0x2ec6330a,0xb33faf9b,0x33fe3235,0x21b1310c,0xb1f4aa63,0xb158b3d7,0x2d5232a2,0xb38bb07a,
  0x33a7333d,0xacab2ed2,0x33f63162,0x262d31eb,0xaa4b301a,0xb3d8b2de,0x2a32326b,0xb3d9b0c7,0xb3f6b26f,0x265fb0c1,0xb3a9b020,0xac9fb2db,
  0x0e48b15d,0x340031f0,0xae1ab33a,0x33652edd,0xaed22e25,0xb33db363,0xb1eb0e48,0xb162b400,0xb2deb3a7,0x301aacab,0xb0c7b3f6,0x326b262d,
  0x30c1aa4b,0x326f33d8,0x32db2a32,0x302033d9,0x31f033f6,0xb15d265f,0x2edd33a9,0xb33aac9f,0xb2acb385,0x306aad76,0x2a19b166,0x33da31e7,
  0x3229a2de,0x311b33fd,0x33133337,0xaf7a2ee8,0x2e3133c5,0xb360aba2,0xb1a128d7,0xb1afb3e8,0xb3f5b015,0xa691b2e1,0xaf9bb3eb,0x330a288d,
  0x3154acc3,0x31f833a3,0x2ef433f8,0xb335a5c9,0x2d8133dc,0xb383aa01,0xb3feb065,0x214db2b0,0xb3ecb107,0x2874b239,0x300fafa6,0x32e53307,
  0x30b7ae3c,0x3276335e,0x302a3400,0xb2d517db,0x312433bd,0xb2212c0e,0xb318b260,0x2f64b0d6,0xb400aeaf,0x997fb345,0x335c20e8,0x2e4833fe,
  0x3102aeff,0x323d3332,0xac7b31fc,0xb3aeb14f,0x2a9433c8,0xb3d4ab71,0xb084b3e6,0x329ba909,0xb2ce2aad,0xb035b3d3,0x33e529cf,0x292233de,
  0x2d2fb241,0x339230fd,0xb14a2fbd,0xb200b301,0x2d993400,0xb37f1b11,0x2084b36f,0x33ff2deb,0xb2ebb21d,0x3005b129,0x30db339f,0xb25c2cdb,
  0xae5fb3e4,0x3357a93b,0xb190303a,0xb1c0b2cb,0x32453258,0xb0f830e0,0x2c63b2ee,0x33b22ffe,0xb3dfae99,0x29b6b34a,0x2ac633ff,0xb3d2a01f,
  0x339ea438,0x2ce733fc,0xb12eb32c,0x3219af15,0x33b8a78b,0x2c3233f2,0x2810b3b3,0x33ef2c57,0xb2c72e6b,0xb040b354,0x29533400,0xb3e31d1b,
  0x3141b133,0x32093215,0xaf21b39c,0x332aacf3,0xae8d32bd,0xb34cb050,0x317d3290,0xb1d23094,0x27bd33fb,0xb3f1249c,0x2fdd3327,0xb2f72f2c,
  0xaaf7b3e2,0x33cfa96c,0xb099b2c4,0x328cb045,0x2cff33b7,0xb39a2c3e,0x31373250,0xb21130ea,0xae76b378,0x3352adbc,0xb1c9b1cd,0x3186b182,
  0xb3ff1ead,0x1de4b3ff,0xb352adbc,0x2e76b378,0x33f1249c,0xa7bd33fb,0x32f72f2c,0xafdd3327,0xb3cfa96c,0x2af7b3e2,0xb28cb045,0x3099b2c4,
  0x339a2c3e,0xacff33b7,0x321130ea,0xb1373250,0x2953b400,0x33e31d1b,0x33ccadd4,0x2b283373,0xaf21339c,0xb32aacf3,0xb3fb2500,0x246ab3fa,
  0x317db290,0x31d23094,0x337a2ade,0xadb133d0,0xb2f130f3,0xaff3b249,0xb254afd2,0x30e5b2fb,0x339e2438,0xace733fc,0xb12e332c,0xb219af15,
  0xb190b03a,0x31c0b2cb,0x3371b0a8,0x2ddf3281,0x2c6332ee,0xb3b22ffe,0xb3f22829,0x2759b3ef,0x2ac6b3ff,0x33d2a01f,0x32932da5,0xb08e337c,
  0xaf0a33f3,0xb32fa727,0x2406b3b0,0x33fcac6f,0x3347b194,0x2ea431bc,0xb1743359,0xb1daae54,0xb3bc2565,0x2c1ab3f9,0x33eeaf59,0x2842331b,
  0x30ad3089,0xb27e3297,0xb2ceaaad,0x3035b3d3,0xb29ba909,0x3084b3e6,0x305f3030,0xb2b332d1,0x259732e8,0xb3f8300a,0x2ccfb3ed,0x33a1a85b,
  0x31b8b381,0x31992d8d,0xb36c31df,0xadf7b170,0xb3f42d3a,0x26f5b390,0x330423a7,0xafb233fc,0x316bb3d6,0x31e32a7c,0xb3832a01,0x2d81b3dc,
  0xb3bf2c87,0x2c02b3ac,0x28743239,0xb3ec3107,0x2b8931b3,0xb3c6319d,0x3276b35e,0x30b72e3c,0x31f8b3a3,0x31542cc3,0xb33525c9,0x2ef4b3f8,
  0x310c2beb,0xb23533c0,0x33abb267,0x2c9330cc,0x307ab3fe,0x32a2a1b1,0xb06aad76,0x32acb385,0xb3a52d52,0x2cb7b38b,0xb11b33fd,0xb229a2de,
  0x94b63273,0xb40030bc,0x3360aba2,0xae3133c5,0xb2de33a7,0xb01aacab,0xb0c733f6,0xb26b262d,0x30c12a4b,0xb26f33d8,0x32dbaa32,0xb02033d9,
  0x31f0b3f6,0x315d265f,0x2eddb3a9,0x333aac9f,0xb1eb8e48,0x3162b400,0xb3872e1a,0x2d6ab365,0xae25ad5e,0x3363b389,0x8e48b15d,0x3400b1f0,
  0xb3a7333d,0xacabaed2,0xb3f63162,0x262db1eb,0x2a4b301a,0xb3d832de,0xaa32326b,0xb3d930c7,0x33f6b26f,0x265f30c1,0x33a9b020,0xac9f32db,
  0x33c0b368,0x2beb2e0e,0x30cc94b6,0xb2673400,0x21b1b10c,0x33feb235,0x3385b3ab,0x2d762c93,0xb38b307a,0x2d52b2a2,0xa2deb06a,0x33fdb2ac,
  0xb0bc33a5,0xb2732cb7,0xb3c5311b,0x2ba2b229,0x26c32ebb,0xb3f53342,0xb3ac316b,0x2c87b1e3,0x336ab0d1,0xae023264,0xb19d33bf,0xb1b32c02,
  0x3225b3e7,0x311fa8f0,0x2cc32b89,0xb3a333c6,0xaa7cad46,0x33d6b38e,0x33dcb1f8,0xaa013154,0xb3fe3318,0x20e8af64,0x3381b3f8,0x2d8d2597,
  0xb14f335c,0xb1fc2e48,0x2d3ab199,0x3390b1b8,0x29092c7b,0xb3e633ae,0xb03026f5,0x32d1b3f4,0x32e8b084,0xb00a329b,0xb3ed32b3,0x285bb05f,
  0x29cfb005,0x33deb2eb,0xb05a325c,0xb2b630db,0xafbd2922,0x3301b3e5,0x27272b59,0xb3f333c9,0xb36f3200,0x2debb14a,0x31bcaf0a,0xb194332f,
  0xb39f33ff,0xacdba084,0x33f9b347,0xa5652ea4,0x3394b2ba,0xad233055,0xa438a9b6,0x33fcb3df,0x33e4b3f9,0x293b2533,0xb03a2ce7,0x32cbb39e,
  0x3258b357,0x30e0ae5f,0xb2ee31c0,0x2ffeb190,0x2e99b0f8,0x334ab245,0xb3ff33b2,0x201fac63,0xaf4230a3,0xb3213285,0x3133b040,0xb21532c7,
  0xa99e2d17,0xb3e03396,0x32bdb209,0xb0503141,0x278b1f76,0xb3f233ff,0x33b3b34c,0xac572e8d,0x2e6bac32,0xb35433b8,0x3400b3ef,0x1d1b2810,
  0xb289324d,0x309eb0ee,0xb3ce33b5,0x2b0fac4b,0xb2f432c1,0x2fe8b04a,0xb3f033e1,0x27efa985,0xb34f3324,0x2e82af37,0xb3ff33fa,0x1eada4ce,
  0xb3983376,0x2d0badc8,0xb3fb33ff,0xa49c1de4,0x351c35f6,0xac93a617,0xb8a3b93c,0x308d2a16,0x32f43448,0xb160afa5,0xb6a4b7fe,0x353a3389,
  0x2fa53160,0xb448b2f4,0xb389b53a,0x37fe36a4,0x26172c93,0xb5f6b51c,0xaa16b08d,0x393c38a3,0x34c3358c,0xac47a5b2,0xb85fb8f3,0x304229b1,
  0x327e33fd,0xb106af26,0xb63cb785,0x34e7330f,0x2f263106,0xb3fdb27e,0xb30fb4e7,0x3785363c,0x25b22c47,0xb58cb4c3,0xa9b1b042,0x38f3385f,
  0x346a3523,0xabf6a54d,0xb81ab8a8,0x2fef294d,0x3209336b,0xb0acaea7,0xb5d4b70a,0x34933294,0x2ea730ac,0xb36bb209,0xb294b493,0x370a35d4,
  0x254d2bf6,0xb523b46a,0xa94dafef,0x38a8381a,0x341334bc,0xab5fa4e9,0xb7a6b85a,0x2f5928e8,0x319432da,0xb052ae28,0xb56ab68d,0x343e3219,
  0x2e283052,0xb2dab194,0xb219b43e,0x368d356a,0x24e92b5f,0xb4bcb413,0xa8e8af59,0x385a37a6,0x33783456,0xaac8a484,0xb715b80a,0x2ec32884,
  0x3120324a,0xaff2ada9,0xb4ffb60e,0x33d3319e,0x2da92ff2,0xb24ab120,0xb19eb3d3,0x360e34ff,0x24842ac8,0xb456b378,0xa884aec3,0x380a3715,
  0x32cd33e3,0xaa31a420,0xb682b76f,0x2e2d281f,0x30ac31bb,0xaf3fad2a,0xb493b58d,0x33283122,0x2d2a2f3f,0xb1bbb0ac,0xb122b328,0x358d3493,
  0x24202a31,0xb3e3b2cd,0xa81fae2d,0x376f3682,0x3223331c,0xa999a376,0xb5ebb6c6,0x2d972776,0x3039312d,0xae8dacac,0xb426b50b,0x327c30a6,
  0x2cac2e8d,0xb12db039,0xb0a6b27c,0x350b3426,0x23762999,0xb31cb223,0xa776ad97,0x36c635eb,0x317a3257,0xa902a2ad,0xb552b61a,0x2d0026ad,
  0x2f8c309f,0xaddcac2e,0xb371b487,0x31cf3029,0x2c2e2ddc,0xb09faf8c,0xb029b1cf,0x34873371,0x22ad2902,0xb257b17a,0xa6adad00,0x361a3552,
  0x30d23194,0xa86ba1e4,0xb4b7b56a,0x2c6a25e4,0x2ea73012,0xad2aab5f,0xb294b402,0x31222f59,0x2b5f2d2a,0xb012aea7,0xaf59b122,0x34023294,
  0x21e4286b,0xb194b0d2,0xa5e4ac6a,0x356a34b7,0x302c30d2,0xa7a9a11b,0xb41ab4b7,0x2ba7251b,0x2dc22f0c,0xac79aa63,0xb1b6b2f7,0x30742e5f,
  0x2a632c79,0xaf0cadc2,0xae5fb074,0x32f731b6,0x211b27a9,0xb0d2b02c,0xa51baba7,0x34b7341a,0x2f0c3012,0xa67ba052,0xb2f7b402,0x2a7a2452,
  0x2cde2df5,0xab91a967,0xb0d7b1e8,0x2f8b2d65,0x29672b91,0xadf5acde,0xad65af8b,0x31e830d7,0x2052267b,0xb012af0c,0xa452aa7a,0x340232f7,
  0x2dc22ea7,0xa54d9f12,0xb1b6b294,0x294d2311,0x2bf62cde,0xaa31a86b,0xafefb0d7,0x2e2d2c6a,0x286b2a31,0xacdeabf6,0xac6aae2d,0x30d72fef,
  0x1f12254d,0xaea7adc2,0xa311a94d,0x329431b6,0x2c792d2a,0xa4209d7f,0xb074b122,0x281f217f,0x2a312b91,0xa8d0a6e0,0xae2daf8b,0x2cce2ade,
  0x26e028d0,0xab91aa31,0xaadeacce,0x2f8b2e2d,0x1d7f2420,0xad2aac79,0xa17fa81f,0x31223074,0x2a632b5f,0xa1e49bdb,0xae5faf59,0x25e41fdb,
  0x286b2967,0xa6e0a4e9,0xac6aad65,0x2ade28e8,0x24e926e0,0xa967a86b,0xa8e8aade,0x2d652c6a,0x1bdb21e4,0xab5faa63,0x9fdba5e4,0x2f592e5f,
  0x27a9286b,0x9f1298b6,0xaba7ac6a,0x23111cb6,0x254d267b,0xa420a1e4,0xa94daa7a,0x281f25e4,0x21e42420,0xa67ba54d,0xa5e4a81f,0x2a7a294d,
  0x18b61f12,0xa86ba7a9,0x9cb6a311,0x2c6a2ba7,0x211b21e4,0x98b69248,0xa51ba5e4,0x1cb61648,0x1f122052,0x9d7f9bdb,0xa311a452,0x217f1fdb,
  0x1bdb1d7f,0xa0529f12,0x9fdba17f,0x24522311,0x124818b6,0xa1e4a11b,0x96489cb6,0x25e4251b,0xa11ba1e4,0x18b61248,0x251b25e4,0x9cb69648,
  0x9f12a052,0x1d7f1bdb,0x23112452,0xa17f9fdb,0x9bdb9d7f,0x20521f12,0x1fdb217f,0xa452a311,0x924898b6,0x21e4211b,0x16481cb6,0xa5e4a51b,
  0xa7a9a86b,0x1f1218b6,0x2ba72c6a,0xa3119cb6,0xa54da67b,0x242021e4,0x294d2a7a,0xa81fa5e4,0xa1e4a420,0x267b254d,0x25e4281f,0xaa7aa94d,
  0x98b69f12,0x286b27a9,0x1cb62311,0xac6aaba7,0xaa63ab5f,0x21e41bdb,0x2e5f2f59,0xa5e49fdb,0xa86ba967,0x26e024e9,0x2c6a2d65,0xaadea8e8,
  0xa4e9a6e0,0x2967286b,0x28e82ade,0xad65ac6a,0x9bdba1e4,0x2b5f2a63,0x1fdb25e4,0xaf59ae5f,0xac79ad2a,0x24201d7f,0x30743122,0xa81fa17f,
  0xaa31ab91,0x28d026e0,0x2e2d2f8b,0xacceaade,0xa6e0a8d0,0x2b912a31,0x2ade2cce,0xaf8bae2d,0x9d7fa420,0x2d2a2c79,0x217f281f,0xb122b074,
  0xadc2aea7,0x254d1f12,0x31b63294,0xa94da311,0xabf6acde,0x2a31286b,0x2fef30d7,0xae2dac6a,0xa86baa31,0x2cde2bf6,0x2c6a2e2d,0xb0d7afef,
  0x9f12a54d,0x2ea72dc2,0x2311294d,0xb294b1b6,0xaf0cb012,0x267b2052,0x32f73402,0xaa7aa452,0xacdeadf5,0x2b912967,0x30d731e8,0xaf8bad65,
  0xa967ab91,0x2df52cde,0x2d652f8b,0xb1e8b0d7,0xa052a67b,0x30122f0c,0x24522a7a,0xb402b2f7,0xb02cb0d2,0x27a9211b,0x341a34b7,0xaba7a51b,
  0xadc2af0c,0x2c792a63,0x31b632f7,0xb074ae5f,0xaa63ac79,0x2f0c2dc2,0x2e5f3074,0xb2f7b1b6,0xa11ba7a9,0x30d2302c,0x251b2ba7,0xb4b7b41a,
  0xb0d2b194,0x286b21e4,0x34b7356a,0xac6aa5e4,0xaea7b012,0x2d2a2b5f,0x32943402,0xb122af59,0xab5fad2a,0x30122ea7,0x2f593122,0xb402b294,
  0xa1e4a86b,0x319430d2,0x25e42c6a,0xb56ab4b7,0xb17ab257,0x290222ad,0x3552361a,0xad00a6ad,0xaf8cb09f,0x2ddc2c2e,0x33713487,0xb1cfb029,
  0xac2eaddc,0x309f2f8c,0x302931cf,0xb487b371,0xa2ada902,0x3257317a,0x26ad2d00,0xb61ab552,0xb223b31c,0x29992376,0x35eb36c6,0xad97a776,
  0xb039b12d,0x2e8d2cac,0x3426350b,0xb27cb0a6,0xacacae8d,0x312d3039,0x30a6327c,0xb50bb426,0xa376a999,0x331c3223,0x27762d97,0xb6c6b5eb,
  0xb2cdb3e3,0x2a312420,0x3682376f,0xae2da81f,0xb0acb1bb,0x2f3f2d2a,0x3493358d,0xb328b122,0xad2aaf3f,0x31bb30ac,0x31223328,0xb58db493,
  0xa420aa31,0x33e332cd,0x281f2e2d,0xb76fb682,0xb378b456,0x2ac82484,0x3715380a,0xaec3a884,0xb120b24a,0x2ff22da9,0x34ff360e,0xb3d3b19e,
  0xada9aff2,0x324a3120,0x319e33d3,0xb60eb4ff,0xa484aac8,0x34563378,0x28842ec3,0xb80ab715,0xb413b4bc,0x2b5f24e9,0x37a6385a,0xaf59a8e8,
  0xb194b2da,0x30522e28,0x356a368d,0xb43eb219,0xae28b052,0x32da3194,0x3219343e,0xb68db56a,0xa4e9ab5f,0x34bc3413,0x28e82f59,0xb85ab7a6,
  0xb46ab523,0x2bf6254d,0x381a38a8,0xafefa94d,0xb209b36b,0x30ac2ea7,0x35d4370a,0xb493b294,0xaea7b0ac,0x336b3209,0x32943493,0xb70ab5d4,
  0xa54dabf6,0x3523346a,0x294d2fef,0xb8a8b81a,0xb4c3b58c,0x2c4725b2,0x385f38f3,0xb042a9b1,0xb27eb3fd,0x31062f26,0x363c3785,0xb4e7b30f,
  0xaf26b106,0x33fd327e,0x330f34e7,0xb785b63c,0xa5b2ac47,0x358c34c3,0x29b13042,0xb8f3b85f,0xb51cb5f6,0x2c932617,0x38a3393c,0xb08daa16,
  0xb2f4b448,0x31602fa5,0x36a437fe,0xb53ab389,0xafa5b160,0x344832f4,0x3389353a,0xb7feb6a4,0xa617ac93,0x35f6351c,0x2a16308d,0xb93cb8a3,
};
__device__ __align__(128) const uint32_t c_img[2560] = {
  0x326d31ed,0x333b32dd,0x33c33388,0x33fe33ea,0x33c331ed,0x31ed33c3,0xa8b22d64,0xb33bb0c4,0x33ea31ed,0xad64301d,0xb2ddb388,0x315fa8b2,
  0x32dd31ed,0xb3feabc6,0x326dad64,0xad64326d,0x30c431ed,0xaed7b2dd,0x2bc63388,0xa248b3ea,0x2bc631ed,0x315fb3c3,0xb3ea2d64,0x2ed730c4,
  0xa8b231ed,0x3388b01d,0x301db388,0xb1ed28b2,0xb01d31ed,0x22482bc6,0x30c4ad64,0x3388b26d,0x33ea33fe,0x338833c3,0x32dd333b,0x31ed326d,
  0xb2ddb3fe,0xa248b01d,0x326d2ed7,0x338833ea,0x30c433fe,0xb33babc6,0xabc6b33b,0x33fe30c4,0xabc6b3fe,0x31ed32dd,0xb3eaaed7,0x333ba8b2,
  0xa8b233fe,0x2d64b3c3,0xb01d333b,0x315fb26d,0x301db3fe,0xb3fe301d,0x30c42ed7,0x2d64b3ea,0xb26d33fe,0x2ed72bc6,0x33c3b33b,0xa248b0c4,
  0x33c3b3fe,0x315fb2dd,0x28b2aed7,0xaed728b2,0xb0c4b15f,0xaed7b01d,0xabc6ad64,0xa248a8b2,0xabc6b15f,0x315f2bc6,0x33ea3388,0x2ed7326d,
  0x28b2b15f,0x338832dd,0xb01d2d64,0xb1edb3ea,0x301db15f,0x224833c3,0xb0c4b388,0x338830c4,0x326db15f,0xb33b301d,0x33c3ad64,0xb3fe28b2,
  0x33c3b15f,0xb1edabc6,0xa8b23388,0x333bb26d,0x33eab15f,0x2d64b2dd,0xb2dd2d64,0xb15f33ea,0x32ddb15f,0x33feb3c3,0x326db388,0x2d64b0c4,
  0x28b22248,0x2d642bc6,0x301d2ed7,0x315f30c4,0xb01da248,0xb3feb2dd,0xb0c4b33b,0x2d64a8b2,0x326d2248,0x2ed733c3,0xb3c3aed7,0xa248b26d,
  0xb3c3a248,0x315fb01d,0xa8b2333b,0xaed7b3ea,0x33ea2248,0xb388abc6,0x32dd2ed7,0xb1edb0c4,0xb2dda248,0x224832dd,0x326db33b,0xb38828b2,
  0x30c42248,0x333bb3c3,0xabc6aed7,0xb3fe326d,0xabc6a248,0xb1ed301d,0xb3ea333b,0xb33b33ea,0xb26d31ed,0xb33b32dd,0xb3c33388,0xb3fe33ea,
  0xb3c331ed,0xb1ed33c3,0x28b22d64,0x333bb0c4,0xb3ea31ed,0x2d64301d,0x32ddb388,0xb15fa8b2,0xb2dd31ed,0x33feabc6,0xb26dad64,0x2d64326d,
  0xb0c431ed,0x2ed7b2dd,0xabc63388,0x2248b3ea,0xabc631ed,0xb15fb3c3,0x33ea2d64,0xaed730c4,0x28b231ed,0xb388b01d,0xb01db388,0x31ed28b2,
  0x301d31ed,0xa2482bc6,0xb0c4ad64,0xb388b26d,0xb3ea33fe,0xb38833c3,0xb2dd333b,0xb1ed326d,0x32ddb3fe,0x2248b01d,0xb26d2ed7,0xb38833ea,
  0xb0c433fe,0x333babc6,0x2bc6b33b,0xb3fe30c4,0x2bc6b3fe,0xb1ed32dd,0x33eaaed7,0xb33ba8b2,0x28b233fe,0xad64b3c3,0x301d333b,0xb15fb26d,
  0xb01db3fe,0x33fe301d,0xb0c42ed7,0xad64b3ea,0x326d33fe,0xaed72bc6,0xb3c3b33b,0x2248b0c4,0xb3c3b3fe,0xb15fb2dd,0xa8b2aed7,0x2ed728b2,
  0x30c4b15f,0x2ed7b01d,0x2bc6ad64,0x2248a8b2,0x2bc6b15f,0xb15f2bc6,0xb3ea3388,0xaed7326d,0xa8b2b15f,0xb38832dd,0x301d2d64,0x31edb3ea,
  0xb01db15f,0xa24833c3,0x30c4b388,0xb38830c4,0xb26db15f,0x333b301d,0xb3c3ad64,0x33fe28b2,0xb3c3b15f,0x31edabc6,0x28b23388,0xb33bb26d,
  0xb3eab15f,0xad64b2dd,0x32dd2d64,0x315f33ea,0xb2ddb15f,0xb3feb3c3,0xb26db388,0xad64b0c4,0xa8b22248,0xad642bc6,0xb01d2ed7,0xb15f30c4,
  0x301da248,0x33feb2dd,0x30c4b33b,0xad64a8b2,0xb26d2248,0xaed733c3,0x33c3aed7,0x2248b26d,0x33c3a248,0xb15fb01d,0x28b2333b,0x2ed7b3ea,
  0xb3ea2248,0x3388abc6,0xb2dd2ed7,0x31edb0c4,0x32dda248,0xa24832dd,0xb26db33b,0x338828b2,0xb0c42248,0xb33bb3c3,0x2bc6aed7,0x33fe326d,
  0x2bc6a248,0x31ed301d,0x33ea333b,0x333b33ea,0x30c4315f,0x2ed7301d,0x2bc62d64,0x224828b2,0x2bc6315f,0xb15fabc6,0xb3eab388,0xaed7b26d,
  0xa8b2315f,0xb388b2dd,0x301dad64,0x31ed33ea,0xb01d315f,0xa248b3c3,0x30c43388,0xb388b0c4,0xb26d315f,0x333bb01d,0xb3c32d64,0x33fea8b2,
  0xb3c3315f,0x31ed2bc6,0x28b2b388,0xb33b326d,0xb3ea315f,0xad6432dd,0x32ddad64,0x315fb3ea,0xb2dd315f,0xb3fe33c3,0xb26d3388,0xad6430c4,
  0xa8b2a248,0xad64abc6,0xb01daed7,0xb15fb0c4,0x301d2248,0x33fe32dd,0x30c4333b,0xad6428b2,0xb26da248,0xaed7b3c3,0x33c32ed7,0x2248326d,
  0x33c32248,0xb15f301d,0x28b2b33b,0x2ed733ea,0xb3eaa248,0x33882bc6,0xb2ddaed7,0x31ed30c4,0x32dd2248,0xa248b2dd,0xb26d333b,0x3388a8b2,
  0xb0c4a248,0xb33b33c3,0x2bc62ed7,0x33feb26d,0x2bc62248,0x31edb01d,0x33eab33b,0x333bb3ea,0x326d31ed,0x333b32dd,0x33c33388,0x33fe33ea,
  0x33c331ed,0x31ed33c3,0xa8b22d64,0xb33bb0c4,0x33ea31ed,0xad64301d,0xb2ddb388,0x315fa8b2,0x32dd31ed,0xb3feabc6,0x326dad64,0xad64326d,
  0x30c431ed,0xaed7b2dd,0x2bc63388,0xa248b3ea,0x2bc631ed,0x315fb3c3,0xb3ea2d64,0x2ed730c4,0xa8b231ed,0x3388b01d,0x301db388,0xb1ed28b2,
  0xb01d31ed,0x22482bc6,0x30c4ad64,0x3388b26d,0x33ea33fe,0x338833c3,0x32dd333b,0x31ed326d,0xb2ddb3fe,0xa248b01d,0x326d2ed7,0x338833ea,
  0x30c433fe,0xb33babc6,0xabc6b33b,0x33fe30c4,0xabc6b3fe,0x31ed32dd,0xb3eaaed7,0x333ba8b2,0xa8b233fe,0x2d64b3c3,0xb01d333b,0x315fb26d,
  0x301db3fe,0xb3fe301d,0x30c42ed7,0x2d64b3ea,0xb26d33fe,0x2ed72bc6,0x33c3b33b,0xa248b0c4,0x33c3b3fe,0x315fb2dd,0x28b2aed7,0xaed728b2,
  0xb0c4315f,0xaed7301d,0xabc62d64,0xa24828b2,0xabc6315f,0x315fabc6,0x33eab388,0x2ed7b26d,0x28b2315f,0x3388b2dd,0xb01dad64,0xb1ed33ea,
  0x301d315f,0x2248b3c3,0xb0c43388,0x3388b0c4,0x326d315f,0xb33bb01d,0x33c32d64,0xb3fea8b2,0x33c3315f,0xb1ed2bc6,0xa8b2b388,0x333b326d,
  0x33ea315f,0x2d6432dd,0xb2ddad64,0xb15fb3ea,0x32dd315f,0x33fe33c3,0x326d3388,0x2d6430c4,0x28b2a248,0x2d64abc6,0x301daed7,0x315fb0c4,
  0xb01d2248,0xb3fe32dd,0xb0c4333b,0x2d6428b2,0x326da248,0x2ed7b3c3,0xb3c32ed7,0xa248326d,0xb3c32248,0x315f301d,0xa8b2b33b,0xaed733ea,
  0x33eaa248,0xb3882bc6,0x32ddaed7,0xb1ed30c4,0xb2dd2248,0x2248b2dd,0x326d333b,0xb388a8b2,0x30c4a248,0x333b33c3,0xabc62ed7,0xb3feb26d,
  0xabc62248,0xb1edb01d,0xb3eab33b,0xb33bb3ea,0xb26d31ed,0xb33b32dd,0xb3c33388,0xb3fe33ea,0xb3c331ed,0xb1ed33c3,0x28b22d64,0x333bb0c4,
  0xb3ea31ed,0x2d64301d,0x32ddb388,0xb15fa8b2,0xb2dd31ed,0x33feabc6,0xb26dad64,0x2d64326d,0xb0c431ed,0x2ed7b2dd,0xabc63388,0x2248b3ea,
  0xabc631ed,0xb15fb3c3,0x33ea2d64,0xaed730c4,0x28b231ed,0xb388b01d,0xb01db388,0x31ed28b2,0x301d31ed,0xa2482bc6,0xb0c4ad64,0xb388b26d,
  0xb3ea33fe,0xb38833c3,0xb2dd333b,0xb1ed326d,0x32ddb3fe,0x2248b01d,0xb26d2ed7,0xb38833ea,0xb0c433fe,0x333babc6,0x2bc6b33b,0xb3fe30c4,
  0x2bc6b3fe,0xb1ed32dd,0x33eaaed7,0xb33ba8b2,0x28b233fe,0xad64b3c3,0x301d333b,0xb15fb26d,0xb01db3fe,0x33fe301d,0xb0c42ed7,0xad64b3ea,
  0x326d33fe,0xaed72bc6,0xb3c3b33b,0x2248b0c4,0xb3c3b3fe,0xb15fb2dd,0xa8b2aed7,0x2ed728b2,0x29ed29ed,0x29ed29ed,0x29ed29ed,0x29ed29ed,
  0x2bc32a6d,0x2add2bea,0x23c628c4,0xa81da0b2,0x2bc32add,0xa3c6281d,0xabc3aadd,0x23c6a81d,0x29ed2b3b,0xabfea564,0x295fa6d7,0x1a482b88,
  0x25642b88,0xa564ab88,0x25642b88,0xa564ab88,0xa0b22bc3,0x2a6daadd,0xabea23c6,0x28c4281d,0xa8c42bea,0x2a6da0b2,0x28c4abea,0xaa6d20b2,
  0xab3b2bfe,0xa564295f,0x26d79a48,0x2b88a9ed,0x29ed29ed,0x29ed29ed,0x29ed29ed,0x29ed29ed,0xabc3aa6d,0xaaddabea,0xa3c6a8c4,0x281d20b2,
  0x2bc32add,0xa3c6281d,0xabc3aadd,0x23c6a81d,0xa9edab3b,0x2bfe2564,0xa95f26d7,0x9a48ab88,0x25642b88,0xa564ab88,0x25642b88,0xa564ab88,
  0x20b2abc3,0xaa6d2add,0x2beaa3c6,0xa8c4a81d,0xa8c42bea,0x2a6da0b2,0x28c4abea,0xaa6d20b2,0x2b3babfe,0x2564a95f,0xa6d71a48,0xab8829ed,
  0x295f295f,0x295f295f,0x295f295f,0x295f295f,0x23c628c4,0xa81da0b2,0xabc3aa6d,0xaaddabea,0xa3c6281d,0xabc3aadd,0x23c6a81d,0x2bc32add,
  0xa95f26d7,0x9a48ab88,0x29ed2b3b,0xabfea564,0xab882564,0x2b88a564,0xab882564,0x2b88a564,0xabea23c6,0x28c4281d,0x20b2abc3,0xaa6d2add,
  0xaa6d20b2,0xa8c42bea,0x2a6da0b2,0x28c4abea,0xa6d71a48,0xab8829ed,0xab3b2bfe,0xa564295f,0x295f295f,0x295f295f,0x295f295f,0x295f295f,
  0xa3c6a8c4,0x281d20b2,0x2bc32a6d,0x2add2bea,0xa3c6281d,0xabc3aadd,0x23c6a81d,0x2bc32add,0x295fa6d7,0x1a482b88,0xa9edab3b,0x2bfe2564,
  0xab882564,0x2b88a564,0xab882564,0x2b88a564,0x2beaa3c6,0xa8c4a81d,0xa0b22bc3,0x2a6daadd,0xaa6d20b2,0xa8c42bea,0x2a6da0b2,0x28c4abea,
  0x26d79a48,0x2b88a9ed,0x2b3babfe,0x2564a95f,0xabfe2bfe,0xabfe2bfe,0xabfe2bfe,0xabfe2bfe,0xaadd2bea,0xa3c628c4,0x281da0b2,0x2bc3aa6d,
  0xa81d2bc3,0x2adda3c6,0x281dabc3,0xaadd23c6,0x9a482b88,0x29edab3b,0xabfe2564,0x295f26d7,0x26d72b3b,0xa6d7ab3b,0x26d72b3b,0xa6d7ab3b,
  0x2a6d2add,0xabeaa3c6,0x28c4a81d,0x20b22bc3,0x2bea2a6d,0xa0b228c4,0xabeaaa6d,0x20b2a8c4,0x2b8829ed,0x2b3b2bfe,0x2564295f,0xa6d79a48,
  0xabfe2bfe,0xabfe2bfe,0xabfe2bfe,0xabfe2bfe,0x2addabea,0x23c6a8c4,0xa81d20b2,0xabc32a6d,0xa81d2bc3,0x2adda3c6,0x281dabc3,0xaadd23c6,
  0x1a48ab88,0xa9ed2b3b,0x2bfea564,0xa95fa6d7,0x26d72b3b,0xa6d7ab3b,0x26d72b3b,0xa6d7ab3b,0xaa6daadd,0x2bea23c6,0xa8c4281d,0xa0b2abc3,
  0x2bea2a6d,0xa0b228c4,0xabeaaa6d,0x20b2a8c4,0xab88a9ed,0xab3babfe,0xa564a95f,0x26d71a48,0x1a489a48,0x1a489a48,0x1a489a48,0x1a489a48,
  0x281da0b2,0x2bc3aa6d,0x2addabea,0x23c6a8c4,0x2adda3c6,0x281dabc3,0xaadd23c6,0xa81d2bc3,0x2bfea564,0xa95fa6d7,0x9a482b88,0x29edab3b,
  0x2b3ba6d7,0xab3b26d7,0x2b3ba6d7,0xab3b26d7,0x28c4a81d,0x20b22bc3,0xaa6daadd,0x2bea23c6,0x20b2a8c4,0x2bea2a6d,0xa0b228c4,0xabeaaa6d,
  0xa564a95f,0x26d71a48,0x2b8829ed,0x2b3b2bfe,0x1a489a48,0x1a489a48,0x1a489a48,0x1a489a48,0xa81d20b2,0xabc32a6d,0xaadd2bea,0xa3c628c4,
  0x2adda3c6,0x281dabc3,0xaadd23c6,0xa81d2bc3,0xabfe2564,0x295f26d7,0x1a48ab88,0xa9ed2b3b,0x2b3ba6d7,0xab3b26d7,0x2b3ba6d7,0xab3b26d7,
  0xa8c4281d,0xa0b2abc3,0x2a6d2add,0xabeaa3c6,0x20b2a8c4,0x2bea2a6d,0xa0b228c4,0xabeaaa6d,0x2564295f,0xa6d79a48,0xab88a9ed,0xab3babfe,
  0xa95fa95f,0xa95fa95f,0xa95fa95f,0xa95fa95f,0xa3c6a8c4,0x281d20b2,0x2bc32a6d,0x2add2bea,0x23c6a81d,0x2bc32add,0xa3c6281d,0xabc3aadd,
  0x295fa6d7,0x1a482b88,0xa9edab3b,0x2bfe2564,0x2b88a564,0xab882564,0x2b88a564,0xab882564,0x2beaa3c6,0xa8c4a81d,0xa0b22bc3,0x2a6daadd,
  0x2a6da0b2,0x28c4abea,0xaa6d20b2,0xa8c42bea,0x26d79a48,0x2b88a9ed,0x2b3babfe,0x2564a95f,0xa95fa95f,0xa95fa95f,0xa95fa95f,0xa95fa95f,
  0x23c628c4,0xa81da0b2,0xabc3aa6d,0xaaddabea,0x23c6a81d,0x2bc32add,0xa3c6281d,0xabc3aadd,0xa95f26d7,0x9a48ab88,0x29ed2b3b,0xabfea564,
  0x2b88a564,0xab882564,0x2b88a564,0xab882564,0xabea23c6,0x28c4281d,0x20b2abc3,0xaa6d2add,0x2a6da0b2,0x28c4abea,0xaa6d20b2,0xa8c42bea,
  0xa6d71a48,0xab8829ed,0xab3b2bfe,0xa564295f,0x29ed29ed,0x29ed29ed,0x29ed29ed,0x29ed29ed,0x2bc32a6d,0x2add2bea,0x23c628c4,0xa81da0b2,
  0x2bc32add,0xa3c6281d,0xabc3aadd,0x23c6a81d,0x29ed2b3b,0xabfea564,0x295fa6d7,0x1a482b88,0x25642b88,0xa564ab88,0x25642b88,0xa564ab88,
  0xa0b22bc3,0x2a6daadd,0xabea23c6,0x28c4281d,0xa8c42bea,0x2a6da0b2,0x28c4abea,0xaa6d20b2,0xab3b2bfe,0xa564295f,0x26d79a48,0x2b88a9ed,
  0x29ed29ed,0x29ed29ed,0x29ed29ed,0x29ed29ed,0xabc3aa6d,0xaaddabea,0xa3c6a8c4,0x281d20b2,0x2bc32add,0xa3c6281d,0xabc3aadd,0x23c6a81d,
  0xa9edab3b,0x2bfe2564,0xa95f26d7,0x9a48ab88,0x25642b88,0xa564ab88,0x25642b88,0xa564ab88,0x20b2abc3,0xaa6d2add,0x2beaa3c6,0xa8c4a81d,
  0xa8c42bea,0x2a6da0b2,0x28c4abea,0xaa6d20b2,0x2b3babfe,0x2564a95f,0xa6d71a48,0xab8829ed,0x9a481a48,0x9a481a48,0x9a481a48,0x9a481a48,
  0xa81d20b2,0xabc32a6d,0xaadd2bea,0xa3c628c4,0xaadd23c6,0xa81d2bc3,0x2adda3c6,0x281dabc3,0xabfe2564,0x295f26d7,0x1a48ab88,0xa9ed2b3b,
  0xab3b26d7,0x2b3ba6d7,0xab3b26d7,0x2b3ba6d7,0xa8c4281d,0xa0b2abc3,0x2a6d2add,0xabeaa3c6,0xa0b228c4,0xabeaaa6d,0x20b2a8c4,0x2bea2a6d,
  0x2564295f,0xa6d79a48,0xab88a9ed,0xab3babfe,0x9a481a48,0x9a481a48,0x9a481a48,0x9a481a48,0x281da0b2,0x2bc3aa6d,0x2addabea,0x23c6a8c4,
  0xaadd23c6,0xa81d2bc3,0x2adda3c6,0x281dabc3,0x2bfea564,0xa95fa6d7,0x9a482b88,0x29edab3b,0xab3b26d7,0x2b3ba6d7,0xab3b26d7,0x2b3ba6d7,
  0x28c4a81d,0x20b22bc3,0xaa6daadd,0x2bea23c6,0xa0b228c4,0xabeaaa6d,0x20b2a8c4,0x2bea2a6d,0xa564a95f,0x26d71a48,0x2b8829ed,0x2b3b2bfe,
  0xabfe2bfe,0xabfe2bfe,0xabfe2bfe,0xabfe2bfe,0xaadd2bea,0xa3c628c4,0x281da0b2,0x2bc3aa6d,0xa81d2bc3,0x2adda3c6,0x281dabc3,0xaadd23c6,
  0x9a482b88,0x29edab3b,0xabfe2564,0x295f26d7,0x26d72b3b,0xa6d7ab3b,0x26d72b3b,0xa6d7ab3b,0x2a6d2add,0xabeaa3c6,0x28c4a81d,0x20b22bc3,
  0x2bea2a6d,0xa0b228c4,0xabeaaa6d,0x20b2a8c4,0x2b8829ed,0x2b3b2bfe,0x2564295f,0xa6d79a48,0xabfe2bfe,0xabfe2bfe,0xabfe2bfe,0xabfe2bfe,
  0x2addabea,0x23c6a8c4,0xa81d20b2,0xabc32a6d,0xa81d2bc3,0x2adda3c6,0x281dabc3,0xaadd23c6,0x1a48ab88,0xa9ed2b3b,0x2bfea564,0xa95fa6d7,
  0x26d72b3b,0xa6d7ab3b,0x26d72b3b,0xa6d7ab3b,0xaa6daadd,0x2bea23c6,0xa8c4281d,0xa0b2abc3,0x2bea2a6d,0xa0b228c4,0xabeaaa6d,0x20b2a8c4,
  0xab88a9ed,0xab3babfe,0xa564a95f,0x26d71a48,0x3bfb3bff,0x3be53bf2,0x3bbf3bd4,0x3b873ba5,0x3bd03bfb,0x3b013b7c,0x399d3a60,0x378538bc,
  0x35173b52,0xbbc9b7c8,0xb074ba9b,0x3bfe391b,0x319e3b27,0xbbf3b979,0x363cb80a,0x3a2d3bc5,0xba093986,0x3a7eb8f8,0xbae5385f,0x3b3db77a,
  0xbabd393c,0x3bb0b699,0xbc00305b,0x3ba730d7,0xbb2a35c8,0xb8353bb2,0x3a64b1e8,0x3962bbf7,0xba90350b,0xba413bff,0x3602340e,0x3bf6bad8,
  0xac6aa5e4,0xb122af59,0xb402b294,0xb56ab4b7,0xb2deac9c,0xb7bdb5a5,0xb9b3b8d6,0xbb10ba73,0xbb96b676,0xb359bafe,0x3bec3884,0x2a163a29,
  0xbbe0b72c,0x2f27b9d6,0x3b5e3ae8,0xb91633a2,0xb941b9c9,0x38ad3a45,0xb80fbab3,0x36d23b13,0xb850ba0d,0x346f3b4a,0x1fdbbbed,0xb4ab3be8,
  0x3721bb76,0xbace3463,0xb8d13bdd,0x39ebadfb,0x3894bb98,0xb8fd281f,0xbb6a3bbd,0x2e2d3825,0x3b3f3b65,0x3ae83b16,0x3a813ab6,0x3a0d3a49,
  0x3263356a,0xad972b43,0xb5dfb359,0xb8eeb7f3,0xa9b139aa,0xbbedba25,0x3340b889,0x3b983afb,0xbaa2aa16,0xb4cfbb8e,0x3c0038ad,0xb44b38e5,
  0xbb853625,0x3bbdb4c3,0xbbe432ad,0x3bfbaf8b,0xbaacb6d2,0x39243954,0xb65fbace,0x2fbd3bb8,0xb9661648,0xba603bf8,0x383a31cf,0x3b27bbb3,
  0x3219b9eb,0xbb1836f4,0xb9903be5,0x37dd3010,0xb6c6b61a,0xb80ab76f,0xb8a8b85a,0xb93cb8f3,0xbbd7bb87,0xbbf8bbfd,0xbb71bbc9,0xba4dbaf1,
  0xbbfeb9a6,0x305bb91f,0x3bcb3a97,0xb50b37d2,0xb87abbfe,0x3ba13546,0x24523a7e,0xbbb5ba54,0xb576bb63,0x340e3ba3,0xb13bbbd3,0x2c9c3bf2,
  0x386abb3d,0xba2139f8,0x3b57b835,0xbbf13432,0x39e7bc00,0xb8d6adc9,0xbacb3bde,0x372c3457,0x3bdab962,0x3764bb35,0xb9c03122,0xbaf73bef,
  0x398b39cd,0x38fd3946,0x386538b2,0x37853815,0xba85b9c9,0xbb92bb1e,0xbbfebbdd,0xbbc2bbf5,0xb66b3682,0xbb01bb94,0x387fb371,0x3a2d3beb,
  0xbac7bb76,0x3a00ad33,0x36bb3bd4,0xbbeab79b,0xbc0026ad,0x3bf32c38,0xbbd6b109,0x3ba733eb,0x3153bbff,0xb70a3b9e,0x396bba9b,0xbade390c,
  0xb5d4b5bc,0xbbb03b2c,0x32013830,0x3bf6ba67,0x3bccbb52,0x2c06b92e,0xbb83385f,0xb8c73bab,0xb9c5b982,0xba41ba04,0xbab0ba7a,0xbb10bae1,
  0xb8a3b986,0xb52fb74e,0xa94db1e8,0x33d32e91,0xbb54bb4f,0x37bdb523,0x3a9e3bc8,0xb916308d,0x3840b5c8,0x394a3bf9,0xbb42b294,0xb0a6bb0a,
  0x251bbbff,0xaf273bfc,0x327cbbe6,0xb4ab3bc0,0x3be325e4,0xbb2fb4e7,0x39e33884,0xb81aba35,0x3b73bb78,0xb46fb715,0xbbdc3ad1,0x2e2d38cc,
  0x33283676,0x3bfcba19,0x3581bab3,0xba6b3493,0x363136dd,0x34cf3581,0x32c6341a,0x2fbd3153,0xbae1bb65,0xb970ba39,0xb715b889,0xb16cb4f3,
  0xb9a12a7a,0xb924bbfe,0x3a933042,0x37dd3bcc,0x308db9aa,0x3b453b07,0xb94632ad,0xb845bbfa,0xbb68b55e,0x3b1836bb,0xbabab805,0x3a4d38a3,
  0x3bc0b625,0xbbfe2ec3,0x3b9431cf,0xba89b742,0x9cb6b95d,0xbbf8396b,0xb1b63a5c,0x3bb5b840,0x38cc9648,0x3b81bbac,0xac38b85a,0xbbce3933,
  0xbb60bb3a,0xbba1bb83,0xbbd2bbbc,0xbbf1bbe3,0x3815361a,0x39df3907,0x3b2c3a97,0x3be23b9c,0xb9afbbfd,0x3a21294d,0x388e3bee,0xbaf7b328,
  0x3beb39a6,0xb6af37a6,0xba04bbd3,0x3ac42d00,0x360ebb89,0xb7643b42,0x3855baeb,0xb8ee3a85,0x33eb3b63,0x28e8bbf5,0xb5233bde,0x389ebb21,
  0x3c00b9f0,0x2d97b9e3,0xbbdf38db,0xb44b3ac7,0xba673c00,0x358d3487,0x3bfcbab6,0x330fba15,0x3b7a3bf1,0x394a3a93,0x33893764,0xb3d39cb6,
  0x3afb3be2,0x35eb3946,0xb4c328e8,0xbaa9b8cc,0x27763af7,0xbb2fbaba,0x3a76ad97,0x30a63b60,0xaf8b3ac4,0xb994bb94,0x3bf8358d,0xb8743815,
  0xbb4c38ee,0x3bfcb1b6,0xbad5b4cf,0x381a39af,0xbbb3389e,0x3b592c38,0xb76fb970,0xb24b3beb,0xb9d2344b,0xbb923bd2,0xb0f03924,0x3a6bb60e,
  0xb8f3330f,0xbc003b2c,0xb91f3b45,0x323233eb,0xb5b1afbd,0xba00b88e,0xbbc6bb18,0xbbc2bc00,0xb7d2b16c,0xbb6fba04,0xbba3bbfe,0xb86fba67,
  0xbbffb7dd,0x370ab855,0x38b73bf8,0xbbeab631,0xbbf2b845,0x39bcb523,0x2dc93b81,0xbaa5bae1,0xb68dba4d,0xac063bdf,0x382abba1,0xbade39a1,
  0xb457ba89,0xb6543bfc,0x3b16b9df,0xbbd8308d,0x397dbbb5,0xb52fb2c6,0xbbe73a21,0xb8c73b68,0x3a49bbce,0x2311b715,0xba2536af,0xbbd93bc0,
  0xb958b785,0xbb81ba9e,0xbbefbbf3,0xba89bb73,0xbbf7bbc2,0xb9b8bb42,0xaf59b70a,0x384a3328,0xbb8bba2d,0x39dfb27c,0x34263bb0,0xbbceb98b,
  0xb4b7bbea,0x3b6c39e3,0xbafe2c06,0x3185ba85,0xaadebba7,0xb6af3bdc,0x3a58ba41,0xbbe2366b,0x3a29bade,0xbc003581,0x3a45352f,0xb2f7bac7,
  0x3b37bbf6,0x28e8b865,0xbaee37bd,0xbac43c00,0x3b13b8c7,0x3b5cbbfe,0x3463b94a,0xb8993153,0xb9f4bb10,0xb58db87f,0x3029af27,0x389e35d4,
  0x2dfbb3d3,0x399936bb,0x3bf23b2f,0x3ac13bcc,0x3552b916,0x39703bd6,0xbbbab46f,0x330fb9c5,0x3ba530a6,0xb5f7396b,0xb7c8bbfc,0x3be138a3,
  0x3bfdb4ab,0xbb45b201,0x38e038fd,0xb16cbb54,0x391b381a,0xa17fbb83,0xb8f83b92,0x3bcfb840,0x36e82e2d,0x3bfebab0,0x37febb01,0xb845251b,
  0xb77a3a6b,0x3648294d,0x3bb2ba00,0x3a8cbbe3,0xb742b93c,0x2311b340,0x37a6340e,0x3aa93966,0x3b963a4d,0x3b7f3c00,0x380f3a21,0xb0be3219,
  0x3933b50b,0x35eb3be4,0xbbf5b8d6,0x3874b6c6,0x39413bb5,0xbbffb65f,0x38d1b764,0x33ba3bd7,0x3b9c2c9c,0xb994b83a,0x34873ae8,0x324bbbfe,
  0xb7213bf1,0x3b47b990,0xbbbf2d97,0x38c1387a,0x2d00372c,0x3b59b8a8,0x3a39bbed,0xb232b576,0xbbfb3af7,0xb9743b71,0x307434cf,0x3adbb86a,
  0x3b213a0d,0x3c003bcb,0x3b073bbd,0x386f39e7,0x351738ee,0xb599a452,0xbae5b924,0xbbe9bbda,0x3a153b98,0xbb6fb13b,0x2ec3ba60,0x3aa53b3f,
  0xba09344b,0xa884bb57,0x3a643b18,0xbbc3b263,0xb4f33bfb,0x39bcbacb,0xbbac380a,0x3bd8a9b1,0xbb2aafbd,0x36a439c0,0x3402bbf8,0xba6f3aa2,
  0xbbfa3b27,0xb6543a81,0x3907b05b,0x3bd9bb85,0x2c6ab7dd,0xb9da35df,0xbbec3ba1,0xb8203aac,0x3bf53b87,0x3b6c3bec,0x392e3a7e,0x32f73721,
  0xb9e7b785,0xbbfcbb5e,0xba81bbb0,0xb43eb894,0x379b3bfe,0xbc00b80f,0x374eb835,0x38993bfb,0xbb3fba2d,0x3b329fdb,0xb3403a41,0xb8eabbd0,
  0xb90c3b3d,0x3b5cb8d1,0xbbf93122,0x3ac13517,0x29b1bba7,0xb94f3b6a,0x3be4b7bd,0xbaf4b19e,0xbbab3962,0xb9993bbf,0x34e73359,0x3be1ba09,
  0x3b85bbf6,0x353ab99d,0xb83a2f27,0xbbf03abd,0x2e91356a,0xb5f7b074,0xba19b8ad,0xbbcfbb2a,0xb966bb10,0xaba7b63c,0x38a8346f,0x3bb73a90,
  0xbb0aaa16,0xa17fbae5,0x3b1e3ace,0xba8c2c6a,0x36c6b916,0x36ff3c00,0xbbcbb8fd,0x3a50b2de,0xba35b6d2,0x36483a64,0x2d33bbe5,0xb84a3b96,
  0x3bfeb4ab,0xb9fcb602,0x313b3b01,0x37e8bbe0,0x3493b9eb,0xb9b83402,0xbb9e3bc9,0xb1853941,0x35762e2d,0x3b90b9b3,0x3acbbbf3,0x2fefb850,
  0x3a543bcf,0x2884374e,0xb9f8b648,0xbbe9bbab,0x398b3bb7,0xb4db3340,0xbbdcb9fc,0xb911bb85,0xb4323a8c,0xb6a4bbf9,0x3b3539b8,0xbbc3ae91,
  0xb66b3a50,0xad65bbe4,0x38653b90,0xbb0db966,0xbbef384a,0x39da34e7,0x2b43bb6c,0xba6f3b0a,0xbc0037e8,0x3759383a,0x387fbbfc,0xbbf636c6,
  0xb7f33185,0xbb7f3a19,0xbb8e3c00,0xb8203a35,0xb5d42fef,0xba1d38a8,0xbbd63b32,0xbba93bfe,0xb8e5b2f7,0xbbffbb1e,0xb954bb5c,0x30beb493,
  0xb9c5b43e,0xbb9fbbcb,0xb201b94f,0x3a313576,0xbbb8b899,0x3b47ad33,0xb6f43999,0xb3babbf5,0xbb54b8ea,0x3bf9313b,0xbab0353a,0x3790b9e7,
  0xb010bac1,0xb9743b9e,0x3bfdb5f7,0xb8c1b79b,0x251bbaf4,0xbb1b3acb,0x3a9e2ba7,0x2e5fbb3f,0x3af1bbe1,0x3599b92e,0xb546a17f,0xbadb390c,
  0x3b73bbf0,0x3929ba81,0x327cb6ff,0xb49f29b1,0xb825baa9,0x353aaec3,0x3b7c3994,0x3af43bfa,0x360eb0be,0x3bf43a64,0x388e3b47,0xb7372c6a,
  0x38bcb874,0x2ba73bac,0xb979bb59,0x3bf03742,0x3c0033ba,0xbb043402,0x3855b974,0xacce3b96,0x3bc5b24b,0xb6ffb907,0xb6993c00,0x3bb7b933,
  0x363138c1,0x3902bbec,0xbbdf3599,0x34ff3941,0x30d73232,0x39fcb7a6,0x3bffbb6f,0x3a50bb9c,0xb9a13adb,0xb47b380f,0x32c62884,0x3937b721,
  0x3ad8386f,0x3b903bf5,0x35a539bc,0xb7e8ad00,0x3b683be9,0x2ef538d1,0xba93b6a4,0xbb24bbfb,0x3a733aa5,0xbbfcb487,0x39d6b654,0xafef3b21,
  0x1cb63bc3,0xb7b2bbbf,0x3aba39da,0xbbfab517,0xb3a23bd8,0x3b32ba39,0xbb4a2311,0x343e3a15,0xbb603a6f,0x3a3d3074,0x31b6bb7f,0xbb9a3a09,
  0xbbe83bd9,0xb94f3b07,0xa81f35eb,0x38eab4f3,0xb9af3820,0xbbae3ae5,0xbbd23bff,0xba113b2a,0x319e389e,0xb929b426,0xbc00bb45,0xb911bb37,
  0xbbffbac1,0xb805bafe,0x382a217f,0x3bfd3b13,0xbabd330f,0x34dbba58,0x36023bfe,0xbb0db9f4,0xb68dbbe1,0x3a5c3a45,0xbbe7b648,0x3b89adfb,
  0xba90b16c,0x2d653aee,0x39b3bb81,0xbbf63552,0x397dbbcf,0xbbbc3463,0x338939b8,0x39f0bba5,0x32deb845,0xb7593029,0xbb5e39df,0xbba93bfd,
  0x3b7aba8c,0x3beebbf2,0x3a76bb6c,0x36ddb91b,0xbbe0ba89,0xba1dbbba,0x1fdbb6af,0x3a3136e8,0xa776b84a,0x3aeb37c8,0x3ad53c00,0xaa7a377a,
  0xb850bbce,0x3b9f38e0,0xbb6a28e8,0x3790b958,0x3b4cb185,0xb8db38f8,0x30f0bb5c,0x355e3bf7,0x3894bbe2,0xbbf937fe,0x399d358d,0x2e5fbb8b,
  0x39d232f7,0x341abbb2,0xbbc63999,0x395d34b7,0x3bd0bac4,0x3b1bbbef,0x363cb970,0xb49faade,0xb5b13899,0x30422f59,0x38b7b5f7,0x3b3aba29,
  0x3219b3d3,0x3b0438b7,0x3b713bfc,0x34ff397d,0x36e83aa9,0xb8b2adc9,0xbbefbb59,0xb5bcba49,0x3bd730a6,0xb902382a,0xa452bb92,0x39373b7a,
  0xb9583874,0x3371bb16,0x34263c00,0xb982bafb,0x387a381a,0x347bbbe7,0xbb573a00,0x3b242776,0xbb8b324b,0x31093a25,0x3a58bb6f,0xbb4f2f8b,
  0xb86a3a6b,0x2ef53389,0x39c0b70a,0x3bfabb4c,0xaadeb232,0xb83034c3,0xbaee39bc,0xbbff3bb3,0x3bda3bc2,0x37b23a76,0xb5df2c06,0xbb9ab9d2,
  0xbb37b86f,0xba7abbf8,0x3029b654,0x3b7838f3,0x32633bea,0xba3dbad5,0x3c00352f,0xba1135b1,0xb9f4baa5,0x3bc8376f,0xbbba2311,0x39cdb7d2,
  0xbaa23ade,0x3baeb0f0,0xb65fb94a,0xb7373bff,0x3552bbd8,0xbbe6391f,0x38e035eb,0x3682bbf2,0xbaac38c7,0xbbf43bc6,0xb9903b2f,0xacce368d,
  0x3bfdbbd9,0x3ad1bba3,0x37feb994,0x26adb457,0x38a33b9a,0xb8dba452,0xbb83bbae,0x2a7ab86a,0x37423b78,0xbab6b426,0xb907bbe6,0x39aa2ade,
  0xb8403a11,0x341abb57,0x294d3bf4,0xb55ebbda,0xb93339cd,0x3889ba58,0xb7a63ad1,0x3625bb37,0xbbe33737,0x304239c0,0x3b42bb04,0xb95db263,
  0xbb9c3682,0xb2ad3aee,0x3bf5b8b2,0x1648b9f4,0xb3282cce,0xb80535df,0xb9e33902,0xbb3a3aa2,0xad0026ad,0xb1cf3029,0xb4873371,0xb61a3552,
  0xba85b4ff,0xba5cbc00,0x3581b47b,0x3bfd3aac,0xbb21b5bc,0xb85abbba,0x3a393109,0x39a63bfd,0xbac7b937,0x3bbc365f,0xbbfeaef5,0x3b89b219,
  0xba15b982,0x3a9738e0,0xbb07b830,0x3b6336e8,0x3153bb24,0xbbee3990,0x36bb37b2,0x39f0bbd7,0x34f3bb4f,0xbbd337fe,0xaec33a7a,0x3c00b958,
  0x3bccbbfa,0x3aebbb71,0x396bba3d,0x36ddb87a,0x3bfabbff,0x3bdebbef,0x3bacbbc8,0x3b65bb8b,0x3bc03911,0x38303b6a,0xb946ad65,0xbb4fbbd0,
  0x3a353bfd,0xb85f30f0,0xbb1ebbbc,0x35c8b5b1,0x38cc3b0d,0xba7ab99d,0x3b943759,0xbbffb19e,0xb4933b89,0x31e8bbc6,0xad333bee,0xa5e4bbff,
  0xb8153bf6,0x3bc8b63c,0xac38ba1d,0xbb783abd,0xbbf539f0,0x329438b7,0x3b9ebaeb,0xb676b68d,0xbbeb3ba9,0xbbe63c00,0xbb2c3b9f,0xb9cd3a90,
  0xb79b36dd,0xb884382a,0xb92e38db,0xb9c9397d,0x33eb3a31,0xbad1b602,0xba04bbf9,0x3682b2de,0xb90c2a7a,0xbab3bbe7,0x374eb41a,0x3b763b7a,
  0xba673790,0x38b2b9b3,0xb5233b1b,0x26adbbe0,0xbbabb55e,0x3bdd3389,0xbbf9b042,0x3bff2776,0xbae12e5f,0xb3713b5e,0x3bfcb929,0xb5bcb850,
  0xae91b95d,0xbbd43a76,0x34e73805,0x3b52bb4c,0x308db49f,0xb1091fdb,0xb71534db,0xb9823894,0x3b0abb3a,0x3a9bbad5,0x3a19ba5c,0x3986b9d2,
  0x2f8bb7e8,0x3bde3979,0x376f3b32,0xb9aab0d7,0x3bb83b24,0xb1223855,0xbbfdba3d,0xaa16b9a1,0x3bb3afef,0xbab63699,0x391fb94f,0xb6253ad8,
  0x30103bfa,0xb359bbdf,0x35463bae,0xb6d2bb68,0x38f3343e,0x3889bbff,0xbba3353a,0x96483a73,0xbaf13b9a,0x38ad32c6,0x39f8bbf4,0xb9eb9cb6,
  0xb7d238ea,0xb2ad35a5,0x2dc92ba7,0x361ab3a2,0xba543a11,0xbace3a93,0xbb353b04,0xbb873b60,0x3bf23af4,0x31cf39d6,0xbb16b6ff,0xb9a6bbe8,
  0xb4323737,0xbbe5baba,0x2b43b902,0x3bfe39af,0x34573bf0,0xb85abb4a,0x3a2539fc,0xbb63b825,0xbbef2cce,0x3bc9b1b6,0xbb8e347b,0x3b3db60e,
  0xba493bb7,0x3a97a81f,0x34c3bb90,0xbc0038bc,0xb7f3b4ff,0xba7e3bd2,0x39542ef5,0x3962bc00,0xbafb3a50,0xbbd33b7c,0xbbf83bfc,0xbb653bc5,
  0x38e5b937,0x3835b88e,0x36f4b7b2,0x356ab631,0xbb13bbe9,0x31e8b6f4,0x3bf239da,0x36763af1,0x3be83911,0x340e3ab0,0xbb7cb759,0xb72cbb73,
  0x2dfbbbc3,0x32943bfd,0xb7c8bb7f,0x39c93a54,0x38253b0d,0xb8d6ba9e,0x39793a1d,0xba0db98b,0x3ba5ba6f,0xb884b546,0xb8f83bff,0x3b76b432,
  0xb8bc3bf6,0x3ae8b27c,0x3699bb9f,0xbb98366b,0x391bb820,0x3ab3b9f8,0x3bb2bb47,0x3bffbbef,0xbbc53ba9,0xbbed3bdc,0xbbff3bf9,0xbbfb3c00,
  0x377ab0be,0x3bdd3b35,0x2f593974,0xbb52b7f3,0x30d73a31,0xbbbdb865,0xb5a5bb1b,0x3b2735d4,0x3bf733ba,0xbbd42b43,0x3afeb599,0xb98638e5,
  0xbad83790,0x3a60b87f,0xb9d63929,0x393cb9c5,0x34b738c1,0x3a9bbb8e,0xba45a884,0xb5c83bb8,0xba732e5f,0xb80a3bd6,0x3b4ab4db,0x350bbb54,
  0xba293adb,0xb85f3954,0xb46336a4,0x25e43010,0x33a2b49f,0x305bb201,0x281fad65,0xac9c251b,0x3f803f80,0x3f803f80,0x3f803f80,0x3f803f80,
  0x3f803f80,0x3f803f80,0x3f803f80,0x3f803f80,0x3f803f80,0x3f803f80,0x3f803f80,0x3f803f80,0x3f803f80,0x3f803f80,0x3f803f80,0x3f803f80,
  0x3f803f80,0x3f803f80,0x3f803f80,0x3f803f80,0x3f803f80,0x3f803f80,0x3f803f80,0x3f803f80,0x3f803f80,0x3f803f80,0x3f803f80,0x3f803f80,
  0x3f803f80,0x3f803f80,0x3f803f80,0x3f803f80,0x3f803f80,0x3f803f80,0x3f803f80,0x3f803f80,0x3f803f80,0x3f803f80,0x3f803f80,0x3f803f80,
  0x3f803f80,0x3f803f80,0x3f803f80,0x3f803f80,0x3f803f80,0x3f803f80,0x3f803f80,0x3f803f80,0x3f803f80,0x3f803f80,0x3f803f80,0x3f803f80,
  0x3f803f80,0x3f803f80,0x3f803f80,0x3f803f80,0x3f803f80,0x3f803f80,0x3f803f80,0x3f803f80,0x3f803f80,0x3f803f80,0x3f803f80,0x3f803f80,
  0x3f803f80,0x3f803f80,0x3f803f80,0x3f803f80,0x3f803f80,0x3f803f80,0x3f803f80,0x3f803f80,0x3f803f80,0x3f803f80,0x3f803f80,0x3f803f80,
  0x3f803f80,0x3f803f80,0x3f803f80,0x3f803f80,0x3f803f80,0x3f803f80,0x3f803f80,0x3f803f80,0x3f803f80,0x3f803f80,0x3f803f80,0x3f803f80,
  0x3f803f80,0x3f803f80,0x3f803f80,0x3f803f80,0x3f803f80,0x3f803f80,0x3f803f80,0x3f803f80,0x3f803f80,0x3f803f80,0x3f803f80,0x3f803f80,
  0x3f803f80,0x3f803f80,0x3f803f80,0x3f803f80,0x3f803f80,0x3f803f80,0x3f803f80,0x3f803f80,0x3f803f80,0x3f803f80,0x3f803f80,0x3f803f80,
  0x3f803f80,0x3f803f80,0x3f803f80,0x3f803f80,0x3f803f80,0x3f803f80,0x3f803f80,0x3f803f80,0x3f803f80,0x3f803f80,0x3f803f80,0x3f803f80,
  0x3f803f80,0x3f803f80,0x3f803f80,0x3f803f80,0x3f803f80,0x3f803f80,0x3f803f80,0x3f803f80,0x3f803f80,0x3f803f80,0x3f803f80,0x3f803f80,
  0x3f803f80,0x3f803f80,0x3f803f80,0x3f803f80,0x3f803f80,0x3f803f80,0x3f803f80,0x3f803f80,0x3f803f80,0x3f803f80,0x3f803f80,0x3f803f80,
  0x3f803f80,0x3f803f80,0x3f803f80,0x3f803f80,0x3f803f80,0x3f803f80,0x3f803f80,0x3f803f80,0x3f803f80,0x3f803f80,0x3f803f80,0x3f803f80,
  0x3f803f80,0x3f803f80,0x3f803f80,0x3f803f80,0x3f803f80,0x3f803f80,0x3f803f80,0x3f803f80,0x3f803f80,0x3f803f80,0x3f803f80,0x3f803f80,
  0x3f803f80,0x3f803f80,0x3f803f80,0x3f803f80,0x3f803f80,0x3f803f80,0x3f803f80,0x3f803f80,0x3f803f80,0x3f803f80,0x3f803f80,0x3f803f80,
  0x3f803f80,0x3f803f80,0x3f803f80,0x3f803f80,0x3f803f80,0x3f803f80,0x3f803f80,0x3f803f80,0x3f803f80,0x3f803f80,0x3f803f80,0x3f803f80,
  0x3f803f80,0x3f803f80,0x3f803f80,0x3f803f80,0x3f803f80,0x3f803f80,0x3f803f80,0x3f803f80,0x3f803f80,0x3f803f80,0x3f803f80,0x3f803f80,
  0x3f803f80,0x3f803f80,0x3f803f80,0x3f803f80,0x3f803f80,0x3f803f80,0x3f803f80,0x3f803f80,0x3f803f80,0x3f803f80,0x3f803f80,0x3f803f80,
  0x3f803f80,0x3f803f80,0x3f803f80,0x3f803f80,0x3f803f80,0x3f803f80,0x3f803f80,0x3f803f80,0x3f803f80,0x3f803f80,0x3f803f80,0x3f803f80,
  0x3f803f80,0x3f803f80,0x3f803f80,0x3f803f80,0x3f803f80,0x3f803f80,0x3f803f80,0x3f803f80,0x3f803f80,0x3f803f80,0x3f803f80,0x3f803f80,
  0x3f803f80,0x3f803f80,0x3f803f80,0x3f803f80,0x3f803f80,0x3f803f80,0x3f803f80,0x3f803f80,0x3f803f80,0x3f803f80,0x3f803f80,0x3f803f80,
  0x3f803f80,0x3f803f80,0x3f803f80,0x3f803f80,0x3f803f80,0x3f803f80,0x3f803f80,0x3f803f80,0x3f803f80,0x3f803f80,0x3f803f80,0x3f803f80,
  0x3f803f80,0x3f803f80,0x3f803f80,0x3f803f80,0x3f803f80,0x3f803f80,0x3f803f80,0x3f803f80,0x3f803f80,0x3f803f80,0x3f803f80,0x3f803f80,
  0x3f803f80,0x3f803f80,0x3f803f80,0x3f803f80,0x3f803f80,0x3f803f80,0x3f803f80,0x3f803f80,0x3f803f80,0x3f803f80,0x3f803f80,0x3f803f80,
  0x3f803f80,0x3f803f80,0x3f803f80,0x3f803f80,0x3f803f80,0x3f803f80,0x3f803f80,0x3f803f80,0x3f803f80,0x3f803f80,0x3f803f80,0x3f803f80,
  0x3f803f80,0x3f803f80,0x3f803f80,0x3f803f80,0x3f803f80,0x3f803f80,0x3f803f80,0x3f803f80,0x3f803f80,0x3f803f80,0x3f803f80,0x3f803f80,
  0x3f803f80,0x3f803f80,0x3f803f80,0x3f803f80,0x3f803f80,0x3f803f80,0x3f803f80,0x3f803f80,0x3f803f80,0x3f803f80,0x3f803f80,0x3f803f80,
  0x3f803f80,0x3f803f80,0x3f803f80,0x3f803f80,0x3f803f80,0x3f803f80,0x3f803f80,0x3f803f80,0x3f803f80,0x3f803f80,0x3f803f80,0x3f803f80,
  0x3f803f80,0x3f803f80,0x3f803f80,0x3f803f80,0x3f803f80,0x3f803f80,0x3f803f80,0x3f803f80,0x3f803f80,0x3f803f80,0x3f803f80,0x3f803f80,
  0x3f803f80,0x3f803f80,0x3f803f80,0x3f803f80,0x3f803f80,0x3f803f80,0x3f803f80,0x3f803f80,0x3f803f80,0x3f803f80,0x3f803f80,0x3f803f80,
  0x3f803f80,0x3f803f80,0x3f803f80,0x3f803f80,0x3f803f80,0x3f803f80,0x3f803f80,0x3f803f80,0x3f803f80,0x3f803f80,0x3f803f80,0x3f803f80,
  0x3f803f80,0x3f803f80,0x3f803f80,0x3f803f80,0x3f803f80,0x3f803f80,0x3f803f80,0x3f803f80,0x3f803f80,0x3f803f80,0x3f803f80,0x3f803f80,
  0x3f803f80,0x3f803f80,0x3f803f80,0x3f803f80,0x3f803f80,0x3f803f80,0x3f803f80,0x3f803f80,0x3f803f80,0x3f803f80,0x3f803f80,0x3f803f80,
  0x3f803f80,0x3f803f80,0x3f803f80,0x3f803f80,0x3f803f80,0x3f803f80,0x3f803f80,0x3f803f80,0x3f803f80,0x3f803f80,0x3f803f80,0x3f803f80,
  0x3f803f80,0x3f803f80,0x3f803f80,0x3f803f80,0x3f803f80,0x3f803f80,0x3f803f80,0x3f803f80,0x3f803f80,0x3f803f80,0x3f803f80,0x3f803f80,
  0x3f803f80,0x3f803f80,0x3f803f80,0x3f803f80,0x3f803f80,0x3f803f80,0x3f803f80,0x3f803f80,0x3f803f80,0x3f803f80,0x3f803f80,0x3f803f80,
  0x3f803f80,0x3f803f80,0x3f803f80,0x3f803f80,0x3f803f80,0x3f803f80,0x3f803f80,0x3f803f80,0x3f803f80,0x3f803f80,0x3f803f80,0x3f803f80,
  0x3f803f80,0x3f803f80,0x3f803f80,0x3f803f80,0x3f803f80,0x3f803f80,0x3f803f80,0x3f803f80,0x3f803f80,0x3f803f80,0x3f803f80,0x3f803f80,
  0x3f803f80,0x3f803f80,0x3f803f80,0x3f803f80,0x3f803f80,0x3f803f80,0x3f803f80,0x3f803f80,0x3f803f80,0x3f803f80,0x3f803f80,0x3f803f80,
  0x3f803f80,0x3f803f80,0x3f803f80,0x3f803f80,0x3f803f80,0x3f803f80,0x3f803f80,0x3f803f80,0x3f803f80,0x3f803f80,0x3f803f80,0x3f803f80,
  0x3f803f80,0x3f803f80,0x3f803f80,0x3f803f80,0x3f803f80,0x3f803f80,0x3f803f80,0x3f803f80,0x3f803f80,0x3f803f80,0x3f803f80,0x3f803f80,
  0x3f803f80,0x3f803f80,0x3f803f80,0x3f803f80,0x3f803f80,0x3f803f80,0x3f803f80,0x3f803f80,0x3f803f80,0x3f803f80,0x3f803f80,0x3f803f80,
  0x3f803f80,0x3f803f80,0x3f803f80,0x3f803f80,
};

__device__ __align__(128) float    g_part[16][8][2176];
__device__ __align__(128) float    g_kv[16][2176];
__device__ __align__(128) uint4    g_o[16 * 16 * 1024];
__device__ __align__(128) unsigned g_ocnt[2 * 16 * 32];
__device__ unsigned g_epoch[128];
#define GSTAMP(role, i) do {} while (0)
#define STAMP(role, i) do {} while (0)
#define PDUMP(role) do {} while (0)
#define PROF_SMEM 0

constexpr int STAGE_BYTES = 57344;
constexpr int OFF_H = 4 * 16384, OFF_VP = 9 * 16384, OFF_SPARE = 10 * 16384;
constexpr int OFF_XT = 172032, XT_STRIDE = 4112;
constexpr int OFF_BAR = 204928, OFF_EPOCH = OFF_BAR + 640, OFF_EX = OFF_BAR + 656, OFF_D = OFF_BAR + 672, OFF_SCALE = OFF_BAR + 704;
constexpr int OFF_F2F = 205824, OFF_F2I = 207872, OFF_F4 = 209920, OFF_ONES = 214016, OFF_KVB = 214016;
constexpr int OFF_STG = 219136, STG_STRIDE = 4352, SMEM_TOTAL = 232192 + PROF_SMEM;
enum { B_FULL1 = 0, B_EMPTY1 = 3, B_Q = 6, B_ODONE1 = 7, B_O1RDY = 8, B_XRAW = 10, B_XT = 11, B_KV = 12, B_Y = 13, B_PKFREE = 14, B_AFREE = 15,
       B_STG = 18, B_ODONE = 24, B_XFREE = 25, B_FULL2 = 33, B_CONS2 = 49, B_COUNT = 62 };
__host__ __device__ constexpr int bar_count(int i) {
  return i < B_EMPTY1 ? 1 : i < B_Q ? 4 : i == B_XT ? 4 : i == B_KV ? 2 : i == B_Y ? 9 : i == B_PKFREE ? 8
       : (i >= B_AFREE && i < B_STG) ? 16 : (i == B_ODONE || i == B_ODONE1) ? 8 : (i >= B_XFREE && i < B_FULL2) ? 4
       : (i >= B_CONS2 && i <= B_CONS2 + 10) ? 4 : i >= B_CONS2 ? 2 : (i >= B_FULL2 && i < B_FULL2 + 7) ? 2 : 1;
}
__host__ __device__ constexpr uint64_t bar_counts(int r) {
  uint64_t v = 0;
  for (int w = 0; w < 11; w++) v |= (uint64_t)(bar_count(1 + 11 * r + w) - 1) << (4 * w);
  return v;
}
constexpr uint64_t SLOT_A = 0x9245392453924594ull;
constexpr uint64_t SLOT_B = 0x7610876108761032ull;
constexpr int SPIN_LIMIT = 1 << 22;
#define PKV CU_TENSOR_MAP_L2_PROMOTION_L2_128B
#define BPRE B_KV
#define PFD 3
#define PD1 400
#define PD2 100
#define E1C 2
#define OSP 4
#define QPF 4
#define TSPLIT 1
#define OC0 2
#define OC1 2
#define BSPL 4
#define BPACE 400
#define NPOS 0
#define O1POS 1
#define HL1 4
#define OCH 3
#define O1D 3
#define QPOS 2
#define HOLD2 13
#define A0COL 0
#define HSTART 1500
#define PACE 1050
#define OC 1

__device__ __forceinline__ uint32_t smem_u32(const void* p) { return (uint32_t)__cvta_generic_to_shared(p); }
__device__ __forceinline__ void wg_fence() { asm volatile("wgmma.fence.sync.aligned;" ::: "memory"); }
__device__ __forceinline__ void wg_commit() { asm volatile("wgmma.commit_group.sync.aligned;" ::: "memory"); }
template <int N> __device__ __forceinline__ void wg_wait() { asm volatile("wgmma.wait_group.sync.aligned %0;" ::"n"(N) : "memory"); }
template <int N> __device__ __forceinline__ void keep(float (&d)[N]) {
#pragma unroll
  for (int i = 0; i < N; i++) asm volatile("" : "+f"(d[i])::"memory");
}
__device__ __forceinline__ uint64_t mkdesc(uint32_t addr, uint32_t lbo, uint32_t sbo, uint32_t swz) {
  uint32_t lo = ((addr & 0x3FFFF) >> 4) | ((lbo >> 4) << 16), hi = (sbo >> 4) | (swz << 30);
  return ((uint64_t)hi << 32) | lo;
}
__device__ __forceinline__ void mbar_init(uint32_t bar, int cnt) { asm volatile("mbarrier.init.shared::cta.b64 [%0], %1;" ::"r"(bar), "r"(cnt)); }
__device__ __forceinline__ void mbar_expect(uint32_t bar, int bytes) { asm volatile("mbarrier.arrive.expect_tx.shared::cta.b64 _, [%0], %1;" ::"r"(bar), "r"(bytes) : "memory"); }
__device__ __forceinline__ void mbar_arrive(uint32_t bar) { asm volatile("mbarrier.arrive.shared::cta.b64 _, [%0];" ::"r"(bar) : "memory"); }
__device__ __forceinline__ void mbar_arrive_cl(uint32_t bar, uint32_t cta) {
  asm volatile("{\n.reg .b32 r;\nmapa.shared::cluster.u32 r, %0, %1;\nmbarrier.arrive.shared::cluster.b64 _, [r];\n}\n" ::"r"(bar), "r"(cta) : "memory");
}
__device__ __forceinline__ void mbar_wait(uint32_t bar, uint32_t parity) {
  asm volatile("{\n.reg .pred p;\n.reg .u32 n;\nmov.u32 n, 0;\n"
               "W_%=:\nmbarrier.try_wait.parity.shared::cta.b64 p, [%0], %1;\n@p bra D_%=;\n"
               "add.u32 n, n, 1;\nsetp.lt.u32 p, n, %2;\n@p bra W_%=;\ntrap;\nD_%=:\n}\n" ::"r"(bar), "r"(parity), "n"(SPIN_LIMIT) : "memory");
}
__device__ __forceinline__ void fence_async() { asm volatile("fence.proxy.async.shared::cta;" ::: "memory"); }
__device__ __forceinline__ void bar_sync(int id) { asm volatile("bar.sync %0, 128;" ::"r"(id) : "memory"); }
__device__ __forceinline__ void tma2d(uint32_t dst, const CUtensorMap* m, int c0, int c1, uint32_t bar) {
  asm volatile("cp.async.bulk.tensor.2d.shared::cluster.global.mbarrier::complete_tx::bytes [%0], [%1, {%3, %4}], [%2];"
               ::"r"(dst), "l"(m), "r"(bar), "r"(c0), "r"(c1) : "memory");
}
__device__ __forceinline__ void tma2d_mc(uint32_t dst, const CUtensorMap* m, int c0, int c1, uint32_t bar) {
  asm volatile("cp.async.bulk.tensor.2d.shared::cluster.global.mbarrier::complete_tx::bytes.multicast::cluster [%0], [%1, {%3, %4}], [%2], %5;"
               ::"r"(dst), "l"(m), "r"(bar), "r"(c0), "r"(c1), "h"((uint16_t)3) : "memory");
}
__device__ __forceinline__ void tma3d(uint32_t dst, const CUtensorMap* m, int c0, int c1, int c2, uint32_t bar) {
  asm volatile("cp.async.bulk.tensor.3d.shared::cluster.global.mbarrier::complete_tx::bytes [%0], [%1, {%3, %4, %5}], [%2];"
               ::"r"(dst), "l"(m), "r"(bar), "r"(c0), "r"(c1), "r"(c2) : "memory");
}
__device__ __forceinline__ void tma4d(uint32_t dst, const CUtensorMap* m, int c0, int c1, int c2, int c3, uint32_t bar) {
  asm volatile("cp.async.bulk.tensor.4d.shared::cluster.global.mbarrier::complete_tx::bytes [%0], [%1, {%3, %4, %5, %6}], [%2];"
               ::"r"(dst), "l"(m), "r"(bar), "r"(c0), "r"(c1), "r"(c2), "r"(c3) : "memory");
}
__device__ __forceinline__ void bulk_ld(uint32_t dst, const void* src, int bytes, uint32_t bar) {
  asm volatile("cp.async.bulk.shared::cluster.global.mbarrier::complete_tx::bytes [%0], [%1], %2, [%3];" ::"r"(dst), "l"(src), "r"(bytes), "r"(bar) : "memory");
}
__device__ __forceinline__ void bulk_ld_mc(uint32_t dst, const void* src, int bytes, uint32_t bar) {
  asm volatile("cp.async.bulk.shared::cluster.global.mbarrier::complete_tx::bytes.multicast::cluster [%0], [%1], %2, [%3], %4;"
               ::"r"(dst), "l"(src), "r"(bytes), "r"(bar), "h"((uint16_t)3) : "memory");
}
__device__ __forceinline__ void tma2d_st(const CUtensorMap* m, uint32_t src, int c0, int c1) {
  asm volatile("cp.async.bulk.tensor.2d.global.shared::cta.bulk_group [%0, {%2, %3}], [%1];" ::"l"(m), "r"(src), "r"(c0), "r"(c1) : "memory");
}
__device__ __forceinline__ void pf_l2(const void* p, int bytes) { asm volatile("cp.async.bulk.prefetch.L2.global [%0], %1;" ::"l"(p), "r"(bytes) : "memory"); }
__device__ __forceinline__ void pf_t2d(const CUtensorMap* m, int c0, int c1) {
  asm volatile("cp.async.bulk.prefetch.tensor.2d.L2.global [%0, {%1, %2}];" ::"l"(m), "r"(c0), "r"(c1) : "memory");
}
__device__ __forceinline__ void pf_t3d(const CUtensorMap* m, int c0, int c1, int c2) {
  asm volatile("cp.async.bulk.prefetch.tensor.3d.L2.global [%0, {%1, %2, %3}];" ::"l"(m), "r"(c0), "r"(c1), "r"(c2) : "memory");
}
__device__ __forceinline__ void ldsm4(uint32_t (&r)[4], uint32_t a) {
  asm volatile("ldmatrix.sync.aligned.m8n8.x4.shared.b16 {%0,%1,%2,%3}, [%4];" : "=r"(r[0]), "=r"(r[1]), "=r"(r[2]), "=r"(r[3]) : "r"(a) : "memory");
}
__device__ __forceinline__ void ldsm4t(uint32_t (&r)[4], uint32_t a) {
  asm volatile("ldmatrix.sync.aligned.m8n8.x4.trans.shared.b16 {%0,%1,%2,%3}, [%4];" : "=r"(r[0]), "=r"(r[1]), "=r"(r[2]), "=r"(r[3]) : "r"(a) : "memory");
}
__device__ __forceinline__ void stsm4(uint32_t a, uint32_t r0, uint32_t r1, uint32_t r2, uint32_t r3) {
  asm volatile("stmatrix.sync.aligned.m8n8.x4.shared.b16 [%0], {%1,%2,%3,%4};" ::"r"(a), "r"(r0), "r"(r1), "r"(r2), "r"(r3) : "memory");
}
__device__ __forceinline__ uint32_t pk2(float lo, float hi) { uint32_t r; asm("cvt.rn.bf16x2.f32 %0, %1, %2;" : "=r"(r) : "f"(hi), "f"(lo)); return r; }
__device__ __forceinline__ uint32_t hmul(uint32_t a, uint32_t b) { uint32_t r; asm("mul.rn.bf16x2 %0, %1, %2;" : "=r"(r) : "r"(a), "r"(b)); return r; }
__device__ __forceinline__ uint32_t hadd(uint32_t a, uint32_t b) { uint32_t r; asm("add.rn.bf16x2 %0, %1, %2;" : "=r"(r) : "r"(a), "r"(b)); return r; }
__device__ __forceinline__ uint32_t hmax(uint32_t a, uint32_t b) { uint32_t r; asm("max.bf16x2 %0, %1, %2;" : "=r"(r) : "r"(a), "r"(b)); return r; }
__device__ __forceinline__ uint32_t hmin(uint32_t a, uint32_t b) { uint32_t r; asm("min.bf16x2 %0, %1, %2;" : "=r"(r) : "r"(a), "r"(b)); return r; }
__device__ __forceinline__ uint32_t hmaxabs(uint32_t a, uint32_t b) { uint32_t r; asm("max.xorsign.abs.bf16x2 %0, %1, %2;" : "=r"(r) : "r"(a), "r"(b)); return r; }
__device__ __forceinline__ float ex2(float x) { float r; asm("ex2.approx.ftz.f32 %0, %1;" : "=f"(r) : "f"(x)); return r; }
__device__ __forceinline__ float rcp_fast(float x) { float r; asm("rcp.approx.ftz.f32 %0, %1;" : "=f"(r) : "f"(x)); return r; }
__device__ __forceinline__ uint32_t phi2(float lo, float hi) {
  uint32_t t;
  asm("cvt.rn.relu.bf16x2.f32 %0, %1, %2;" : "=r"(t) : "f"(hi), "f"(lo));
  const uint32_t e = pk2(ex2(lo * 1.4426950408889634f), ex2(hi * 1.4426950408889634f));
  return hadd(hadd(t, hmin(e, 0x3F803F80u)), 0x35863586u);
}
__device__ __forceinline__ bool opaque_true() { uint32_t v; asm volatile("mov.u32 %0, %%nctaid.y;" : "=r"(v)); return v != 0; }
__device__ __forceinline__ int normalise(uint32_t (&v)[32], float fd) {
  const float f0 = fd + __uint_as_float(v[0] << 16);
  uint32_t m[4] = {hmaxabs(__float_as_uint(f0) >> 16, v[0]), v[1], v[2], v[3]};
#pragma unroll
  for (int i = 4; i < 32; i++) m[i & 3] = hmaxabs(m[i & 3], v[i]);
  m[0] = hmaxabs(hmaxabs(m[0], m[1]), hmaxabs(m[2], m[3]));
  const int e = min(max((int)(__reduce_max_sync(~0u, max(m[0] & 0x7FFFu, (m[0] >> 16) & 0x7FFFu)) >> 7), 1), 253);
  if (e > 141) {
#pragma unroll
    for (int i = 0; i < 32; i++) v[i] = hmul(v[i], 0x07000700u);
  }
  const uint32_t sc = (e > 141 ? 255 - e : 142 - e) * 0x00800080u;
#pragma unroll
  for (int i = 0; i < 32; i++) {
    const uint32_t a = hmul(v[i], sc);
    v[i] = (a & 0x0FFF0FFFu) * 7 + a;
  }
  v[0] = __byte_perm(v[0], __half_as_ushort(__float2half_rn(f0 * __uint_as_float((254 - e) << 23))), 0x3254);
  return e;
}
__device__ __forceinline__ void poll_ge(const unsigned* p, unsigned target) {
#pragma unroll 1
  for (int n = 0; n < SPIN_LIMIT; n++) {
    unsigned v;
    asm volatile("ld.relaxed.gpu.global.u32 %0, [%1];" : "=r"(v) : "l"(p) : "memory");
    if (__all_sync(~0u, (int)(v - target) >= 0)) { asm volatile("fence.acquire.gpu;" ::: "memory"); return; }
  }
  __trap();
}

__device__ __forceinline__ bool elect_one() {
  uint32_t p;
  asm volatile("{\n.reg .pred p;\nelect.sync _|p, 0xffffffff;\nselp.u32 %0, 1, 0, p;\n}\n" : "=r"(p));
  return p;
}
__device__ __forceinline__ uint4 ld_nc4(const void* p) {
  uint4 v;
  asm volatile("ld.global.nc.L1::no_allocate.v4.u32 {%0,%1,%2,%3}, [%4];" : "=r"(v.x), "=r"(v.y), "=r"(v.z), "=r"(v.w) : "l"(p));
  return v;
}
__device__ __forceinline__ void st_cg4(void* p, uint4 v) {
  asm volatile("st.global.cg.v4.u32 [%0], {%1,%2,%3,%4};" ::"l"(p), "r"(v.x), "r"(v.y), "r"(v.z), "r"(v.w) : "memory");
}
__device__ __forceinline__ uint32_t mapa(uint32_t a, uint32_t cta) { uint32_t r; asm("mapa.shared::cluster.u32 %0, %1, %2;" : "=r"(r) : "r"(a), "r"(cta)); return r; }
__device__ __forceinline__ void st_async(uint32_t a, uint32_t v, uint32_t bar) {
  asm volatile("st.async.weak.shared::cluster.mbarrier::complete_tx::bytes.b32 [%0], %1, [%2];" ::"r"(a), "r"(v), "r"(bar) : "memory");
}
__device__ __forceinline__ void st_async4(uint32_t a, uint32_t x, uint32_t y, uint32_t z, uint32_t w, uint32_t bar) {
  asm volatile("st.async.weak.shared::cluster.mbarrier::complete_tx::bytes.v4.b32 [%0], {%1,%2,%3,%4}, [%5];" ::"r"(a), "r"(x), "r"(y), "r"(z), "r"(w), "r"(bar) : "memory");
}
__device__ __forceinline__ void tma3d_st(const CUtensorMap* m, uint32_t src, int c0, int c1, int c2) {
  asm volatile("cp.async.bulk.tensor.3d.global.shared::cta.bulk_group [%0, {%2, %3, %4}], [%1];" ::"l"(m), "r"(src), "r"(c0), "r"(c1), "r"(c2) : "memory");
}
__device__ __forceinline__ uint4 ld_rlx4(const void* p) {
  uint4 v;
  asm volatile("{\n.reg .b128 t;\n.reg .b64 a, b;\nld.relaxed.gpu.global.b128 t, [%4];\nmov.b128 {a, b}, t;\nmov.b64 {%0, %1}, a;\nmov.b64 {%2, %3}, b;\n}\n"
               : "=r"(v.x), "=r"(v.y), "=r"(v.z), "=r"(v.w) : "l"(p) : "memory");
  return v;
}
__device__ __forceinline__ void ld_stale4(uint4& v, const void* p, uint32_t tag) {
  asm volatile("{\n.reg .b128 t;\n.reg .b64 a, b;\n.reg .b32 x;\n.reg .pred p;\n"
               "lop3.b32 x, %0, %5, 1, 0x28;\nsetp.ne.u32 p, x, 0;\n"
               "mov.b64 a, {%0, %1};\nmov.b64 b, {%2, %3};\nmov.b128 t, {a, b};\n"
               "@p ld.relaxed.gpu.global.b128 t, [%4];\n"
               "mov.b128 {a, b}, t;\nmov.b64 {%0, %1}, a;\nmov.b64 {%2, %3}, b;\n}\n"
               : "+r"(v.x), "+r"(v.y), "+r"(v.z), "+r"(v.w) : "l"(p), "r"(tag) : "memory");
}
__device__ __forceinline__ void st_tag4(void* p, float a, float b, float c, float d, uint32_t tag) {
  asm volatile("{\n.reg .b128 t;\n.reg .b64 a, b;\nmov.b64 a, {%1, %2};\nmov.b64 b, {%3, %4};\nmov.b128 t, {a, b};\nst.relaxed.gpu.global.b128 [%0], t;\n}\n"
               ::"l"(p), "r"((__float_as_uint(a) & ~1u) | tag), "f"(b), "f"(c), "f"(d) : "memory");
}
__device__ __forceinline__ uint32_t stale8(const uint4 (&f)[8], uint32_t tag) {
  uint32_t r[4];
#pragma unroll
  for (int i = 0; i < 4; i++) asm("lop3.b32 %0, %1, %2, %3, 0x7E;" : "=r"(r[i]) : "r"(f[2 * i].x), "r"(f[2 * i + 1].x), "r"(tag));
  asm("lop3.b32 %0, %0, %1, %2, 0xFE;" : "+r"(r[0]) : "r"(r[1]), "r"(r[2]));
  return r[0] | r[3];
}

struct ConvC { uint32_t a1[2][4], wa[2], wb[2], sg; };
__device__ __forceinline__ uint64_t dsc(uint32_t lo, uint32_t hi) { return ((uint64_t)hi << 32) | lo; }
__device__ __forceinline__ uint32_t hfma(uint32_t a, uint32_t b, uint32_t c) { uint32_t r; asm("fma.rn.f16x2 %0, %1, %2, %3;" : "=r"(r) : "r"(a), "r"(b), "r"(c)); return r; }
__device__ __forceinline__ uint32_t hfnma(uint32_t a, uint32_t b, uint32_t c) { uint32_t r; asm("{.reg .b32 n; neg.f16x2 n, %1; fma.rn.f16x2 %0, n, %2, %3;}" : "=r"(r) : "r"(a), "r"(b), "r"(c)); return r; }
__device__ __forceinline__ uint32_t hmul16(uint32_t a, uint32_t b) { uint32_t r; asm("mul.rn.f16x2 %0, %1, %2;" : "=r"(r) : "r"(a), "r"(b)); return r; }
template <int N> __device__ __forceinline__ void keepu(uint32_t (&d)[N]) {
#pragma unroll
  for (int i = 0; i < N; i++) asm volatile("" : "+r"(d[i])::"memory");
}
__device__ __forceinline__ void conv_m1(const ConvC& K, uint32_t (&u)[16], uint32_t l) {
  wg_fence();
  wgmma_hrs_n64<1>(u, K.a1[0][0], K.a1[0][1], K.a1[0][2], K.a1[0][3], dsc(l, 32), 0);
  wgmma_hrs_n64<1>(u, K.a1[1][0], K.a1[1][1], K.a1[1][2], K.a1[1][3], dsc(l + 16, 32), 1);
  wg_commit();
}
__device__ __forceinline__ void conv_s2(const ConvC& K, uint32_t (&u)[16], uint32_t (&Z)[2][8], uint32_t dfl) {
  uint32_t fr[8], fi[8];
#pragma unroll
  for (int c = 0; c < 8; c++) {
    const uint32_t r = hfma(K.wa[c & 1], u[2 * c + 1], u[2 * c]);
    fi[c] = hfma(K.wb[c & 1], r, u[2 * c + 1]);
    fr[c] = hfma(K.wa[c & 1], fi[c], r);
  }
  wg_fence();
#pragma unroll
  for (int p = 0; p < 2; p++) {
    wgmma_hrs_n32<0>(Z[p], fr[4 * p], fr[4 * p + 2], fr[4 * p + 1], fr[4 * p + 3], dsc(dfl, 32), 0);
    wgmma_hrs_n32<0>(Z[p], fi[4 * p], fi[4 * p + 2], fi[4 * p + 1], fi[4 * p + 3], dsc(dfl + 16, 32), 1);
  }
  wg_commit();
}
__device__ __forceinline__ void conv_win(const ConvC& K, const uint32_t (&X)[2][8], uint32_t (&W)[2][8]) {
#pragma unroll
  for (int b = 0; b < 4; b++)
#pragma unroll
    for (int c = 0; c < 2; c++) {
      const uint32_t xr = X[b >> 1][2 * c + (b & 1)], xi = X[b >> 1][4 + 2 * c + (b & 1)];
      const int a = b ? b - 1 : 0;
      W[b >> 1][2 * c + (b & 1)] = b ? hfnma(K.sg, X[a >> 1][4 + 2 * c + (a & 1)], xr) : hmul16(xr, 0x3C003C00u);
      W[b >> 1][4 + 2 * c + (b & 1)] = b ? hfma(K.sg, X[a >> 1][2 * c + (a & 1)], xi) : hmul16(xi, 0x3C003C00u);
    }
}
template <int p>
__device__ __forceinline__ void conv_pw(uint32_t (&X)[2][8], uint32_t (&H)[2][8], uint32_t (&V)[8], uint32_t dil) {
  uint32_t pr[2][2], pi[2][2];
#pragma unroll
  for (int jj = 0; jj < 2; jj++)
#pragma unroll
    for (int c = 0; c < 2; c++) {
      const int j = 2 * p + jj;
      uint32_t sr = 0, si = 0;
#pragma unroll
      for (int a = 0; a <= j; a++) {
        const int b = j - a;
        const uint32_t hr = H[a >> 1][2 * c + (a & 1)], hi = H[a >> 1][4 + 2 * c + (a & 1)];
        const uint32_t xr = X[b >> 1][2 * c + (b & 1)], xi = X[b >> 1][4 + 2 * c + (b & 1)];
        sr = a == 0 ? hmul16(hr, xr) : hfma(hr, xr, sr);
        si = a == 0 ? hmul16(hr, xi) : hfma(hr, xi, si);
        sr = hfnma(hi, xi, sr);
        si = hfma(hi, xr, si);
      }
      pr[jj][c] = sr; pi[jj][c] = si;
    }
  wg_fence();
  wgmma_hrs_n32<0>(V, pr[0][0], pr[1][0], pr[0][1], pr[1][1], dsc(dil, 32), 0);
  wgmma_hrs_n32<0>(V, pi[0][0], pi[1][0], pi[0][1], pi[1][1], dsc(dil + 16, 32), 1);
  wg_commit();
}
template <int p>
__device__ __forceinline__ void conv_it(const ConvC& K, uint32_t (&V)[8], uint32_t vst) {
#pragma unroll
  for (int jj = 0; jj < 2; jj++) {
    uint32_t wr[2], wi[2];
#pragma unroll
    for (int c = 0; c < 2; c++) {
      const uint32_t r = hfnma(K.wa[c], V[4 + 2 * c + jj], V[2 * c + jj]);
      wi[c] = hfnma(K.wb[c], r, V[4 + 2 * c + jj]);
      wr[c] = hfnma(K.wa[c], wi[c], r);
    }
    stsm4(vst + (2 * p + jj) * 2048, wr[0], wr[1], wi[0], wi[1]);
  }
}
__device__ __forceinline__ void conv_m4(uint32_t (&y)[8], uint32_t (&a)[4][4], uint32_t d4l) {
  wg_fence();
  wgmma_hrs_n32<0>(y, a[0][0], a[0][1], a[0][2], a[0][3], dsc(d4l, 64), 0);
#pragma unroll
  for (int s = 1; s < 4; s++) wgmma_hrs_n32<0>(y, a[s][0], a[s][1], a[s][2], a[s][3], dsc(d4l + s * 16, 64), 1);
  wg_commit();
}

struct Params {
  CUtensorMap tmX, tmW, tmWo, tmWo1, tmK, tmV, tmQ, tmOA, tmOB;
  const __nv_bfloat16 *shift_k, *h, *D, *x, *w, *wo, *q;
  float *part, *kv;
  uint4* o;
  unsigned *ocnt, *epoch;
  const uint32_t *thr, *img;
};

__global__ void __cluster_dims__(2, 1, 1) __launch_bounds__(384, 1) fused_kernel(const __grid_constant__ Params P) {
  extern __shared__ __align__(1024) uint8_t smem[];
  const uint32_t sb = smem_u32(smem);
  const uint32_t bars = sb + OFF_BAR;
  const int tid = threadIdx.x, lane = tid & 31;
  const int warp = __shfl_sync(~0u, tid >> 5, 0);
  const int rank = blockIdx.x & 1, cl = blockIdx.x >> 1;
  const int mb = cl < 4 ? 4 + cl : cl < 36 ? (cl - 4) >> 3 : 4 + (cl - 36) / 7;
  const int hb = (cl - 36) % 7;
  const int hq = cl < 4 ? A0COL : cl < 36 ? (cl - 4) & 7 : hb + (hb >= A0COL);
  const int hp = 2 * hq + rank;
  const int rb = 2 * mb + (hq >> 2), cb = hq & 3;
#define BAR(i) (bars + 8 * (i))

  if (tid == 0) { STAMP(0, 0); GSTAMP(0, 30); }
  if (warp == 8) {
    if (elect_one()) {
      mbar_init(BAR(B_FULL1), 1);
      asm volatile("fence.mbarrier_init.release.cluster;" ::: "memory");
      mbar_expect(BAR(B_FULL1), STAGE_BYTES);
      tma3d(sb + 32768, &P.tmW, hp * 64, 0, 0, BAR(B_FULL1));
    }
    if (lane == 0) STAMP(3, 21);
  } else if (lane == 0) {
    const int wi = warp - (warp > 8);
#pragma unroll
    for (int r = 0; r < 6; r++)
      if (r < 5 || wi < B_COUNT - 56) mbar_init(BAR(1 + 11 * r + wi), ((uint32_t)(bar_counts(r) >> (4 * wi)) & 15) + 1);
    asm volatile("fence.mbarrier_init.release.cluster;" ::: "memory");
  }
  if (tid == 0) STAMP(2, 6);
  asm volatile("barrier.cluster.arrive.relaxed.aligned;\nbarrier.cluster.wait.aligned;" ::: "memory");
  if (warp == 8 && elect_one()) tma2d_mc(sb + rank * 16384, &P.tmX, 0, mb * 256 + rank * 128, BAR(B_FULL1));
  if (tid == 256) STAMP(2, 7);

  if (warp < 8) {
    asm volatile("setmaxnreg.inc.sync.aligned.u32 224;");
    const int wg = warp >> 2, w = warp & 3, g = lane >> 2, q = lane & 3, t = tid & 127;
    const bool elect = (t == 0);
    const uint32_t s16 = (sb & 0x3FFFF) >> 4;
    constexpr uint32_t SW128 = 64 | (1u << 30);
    uint32_t pq[2][16], v[32];
    int ehs;
    ConvC K;
    {
      float acc[2][96];
      int st = 0, ph = 0;
#pragma unroll 1
      for (int kb = 0; kb < 14; kb++) {
        mbar_wait(BAR(B_FULL1 + st), ph);
        if (kb == 0 && elect) { STAMP(wg, 1); GSTAMP(wg, 26); }
        if (kb == 8 && elect) { STAMP(wg, 16); GSTAMP(wg, 25); }
        if (tid == 0) STAMP(2, 8 + kb);
        const uint32_t da = s16 + st * (STAGE_BYTES >> 4) + wg * 1024 + (1 << 16);
        const uint32_t db = s16 + st * (STAGE_BYTES >> 4) + 2048 + (512 << 16);
        wg_fence();
#pragma unroll
        for (int ks = 0; ks < 4; ks++) {
          wgmma_ss_n192<0, 1>(acc[0], dsc(da + ks * 2, SW128), dsc(db + ks * 128, SW128), (kb | ks) != 0);
          wgmma_ss_n192<0, 1>(acc[1], dsc(da + 512 + ks * 2, SW128), dsc(db + ks * 128, SW128), (kb | ks) != 0);
        }
        wg_commit();
        wg_wait<1>();
        if (kb > 0 && t < 2) mbar_arrive_cl(BAR(B_EMPTY1 + (st == 0 ? 2 : st - 1)), t);
        if (++st == 3) { st = 0; ph ^= 1; }
      }
#define TAIL_MMA(mt, stage) do { wg_fence(); _Pragma("unroll") for (int ks = 0; ks < 4; ks++) \
        wgmma_ss_n192<0, 1>(acc[mt], dsc(s16 + (stage) * (STAGE_BYTES >> 4) + wg * 1024 + (mt) * 512 + (1 << 16) + ks * 2, SW128), \
                            dsc(s16 + (stage) * (STAGE_BYTES >> 4) + 2048 + (512 << 16) + ks * 128, SW128), 1); wg_commit(); } while (0)
      mbar_wait(BAR(B_FULL1 + 2), 0);
      TAIL_MMA(0, 2);
      wg_wait<1>();
      if (t < 2) mbar_arrive_cl(BAR(B_EMPTY1 + 1), t);
      mbar_wait(BAR(B_FULL1 + 0), 1);
      TAIL_MMA(0, 0);
      TAIL_MMA(1, 2);
      if (!TSPLIT) TAIL_MMA(1, 0);
      const uint32_t lrow = sb + (16 * w + 8 * ((lane >> 3) & 1) + (lane & 7)) * 128 + (((lane >> 4) ^ (lane & 7)) << 4);
      const uint32_t pko = OFF_H + wg * 8192, vo0 = 6 * 16384 + wg * 8192, vo1 = 7 * 16384 + wg * 16384;
#define E1K(mt, i) do { if (opaque_true()) { _Pragma("unroll") for (int j = (i); j < (i) + 2; j++) { \
          const float* a = &acc[mt][32 + 8 * j]; const float* b = a + 32; const uint32_t o = lrow ^ (j * 32); \
          stsm4(o + ((mt) ? vo1 : vo0), pk2(b[0], b[1]), pk2(b[2], b[3]), pk2(b[4], b[5]), pk2(b[6], b[7])); \
          stsm4(o + pko + (mt) * 16384, phi2(a[0], a[1]), phi2(a[2], a[3]), phi2(a[4], a[5]), phi2(a[6], a[7])); } } } while (0)
#define E1Q(mt) do { if (opaque_true()) { _Pragma("unroll") for (int i = 0; i < 16; i++) pq[mt][i] = phi2(acc[mt][2 * i], acc[mt][2 * i + 1]); } } while (0)
      const uint4* hp4 = (const uint4*)(P.h + (blockIdx.x * 8 + warp) * 2048) + ((lane & 15) * 2 + (lane >> 4));
#define LOAD_H(i0, i1) do { _Pragma("unroll") for (int i = (i0); i < (i1); i++) { \
        const uint4 u = ld_nc4(hp4 + i * 32); v[4 * i] = u.x; v[4 * i + 1] = u.y; v[4 * i + 2] = u.z; v[4 * i + 3] = u.w; } } while (0)
      mbar_wait(BAR(B_EMPTY1 + 1), 0);
      if (TSPLIT) wg_wait<1>(); else wg_wait<2>();
      keep(acc[0]);
      if (elect) STAMP(wg, 18);
      E1K(0, 0);
      if (TSPLIT) TAIL_MMA(1, 0);
      LOAD_H(0, HL1);
      E1K(0, 2);
      if (elect) STAMP(wg, 19);
      LOAD_H(HL1, 8);
      if (QPOS == 0) E1Q(0);
      if (elect) STAMP(wg, 20);
      {
        const uint4* ct = (const uint4*)P.thr + t;
#pragma unroll
        for (int s = 0; s < 2; s++) { const uint4 u = ld_nc4(ct + s * 128); K.a1[s][0] = u.x; K.a1[s][1] = u.y; K.a1[s][2] = u.z; K.a1[s][3] = u.w; }
        const uint4 u = ld_nc4(ct + 2 * 128);
        K.wa[0] = u.x; K.wa[1] = u.y; K.wb[0] = u.z; K.wb[1] = u.w;
        K.sg = (lane & 4) ? 0xBC00BC00u : 0x3C003C00u;
      }
      mbar_wait(BAR(B_XT), 0);
      const uint32_t tag = ~*(volatile unsigned*)(smem + OFF_EPOCH) & 1;
      wg_wait<0>();
      keep(acc[1]);
      if (t < 2) mbar_arrive_cl(BAR(B_EMPTY1 + 0), t);
      if (elect) { STAMP(wg, 2); GSTAMP(wg, 27); }
      E1K(1, 0);
      E1K(1, 2);
      fence_async();
      bar_sync(1 + wg);
      if (elect) STAMP(wg, 3);
      float kva[36];
      wg_fence();
#pragma unroll
      for (int ks = 0; ks < 8; ks++) {
        const uint32_t vb = ((ks >> 2 ? vo1 : vo0) >> 4) + (ks & 3) * 128;
        wgmma_ss_n72<1, 1>(kva, dsc(s16 + (pko >> 4) + (ks >> 2) * 1024 + (ks & 3) * 128 + (1 << 16), SW128),
                           dsc(s16 + vb + (((OFF_ONES >> 4) - vb) << 16), SW128), ks != 0);
      }
      wg_commit();
      int eh = 0;
      if (QPOS == 1) E1Q(0);
      if (NPOS == 0) eh = normalise(v, lane == 0 ? *(const float*)(smem + OFF_D + 4 * warp) : 0.f);
      wg_wait<0>();
      keep(kva);
      if (elect) STAMP(wg, 24);
      {
        float4 p[5];
#pragma unroll
        for (int c = 0; c < 4; c++)
          p[c] = w < 2 ? make_float4(kva[4 * c], kva[4 * c + 1], kva[4 * c + 2], kva[4 * c + 3])
                       : make_float4(kva[16 + 4 * c], kva[17 + 4 * c], kva[18 + 4 * c], kva[19 + 4 * c]);
        p[4] = make_float4(kva[32], kva[34], __shfl_down_sync(~0u, kva[32], 4), __shfl_down_sync(~0u, kva[34], 4));
        float4* hand = (float4*)(smem + 8 * 16384 + 8192 - (w >> 1) * 16384) + (t & 63);
        if ((w >> 1) != wg) {
#pragma unroll
          for (int c = 0; c < 5; c++) hand[c * 64] = p[c];
          asm volatile("bar.arrive %0, 128;" ::"r"(5 + (w >> 1)) : "memory");
        } else {
          float* dst = P.part + (hp * 8 + mb) * 2176;
          asm volatile("bar.sync %0, 128;" ::"r"(5 + (w >> 1)) : "memory");
#pragma unroll
          for (int c = 0; c < 5; c++) { const float4 u = hand[c * 64]; p[c].x += u.x; p[c].y += u.y; p[c].z += u.z; p[c].w += u.w; }
#pragma unroll
          for (int c = 0; c < 5; c++)
            if (c < 4 || !(lane & 7)) st_tag4(c < 4 ? dst + (c * 128 + t) * 4 : dst + 2048 + 16 * w + 2 * g, p[c].x, p[c].y, p[c].z, p[c].w, tag);
        }
        __syncwarp();
        if (lane == 0) mbar_arrive(BAR(B_PKFREE));
      }
      if (elect) STAMP(wg, 4);
      if (QPOS == 2) E1Q(0);
      E1Q(1);
      if (NPOS == 1) eh = normalise(v, lane == 0 ? *(const float*)(smem + OFF_D + 4 * warp) : 0.f);
      ehs = eh;
    }
    mbar_wait(BAR(B_PKFREE), 0);
    if (elect) STAMP(wg, 17);
    {
      const int e = ehs;
      uint8_t* dst = smem + OFF_H + (w & 2) * 8192 + wg * 8192 + (w & 1) * 4096 + (lane >> 4) * 512 + (lane & 15) * 16;
#pragma unroll
      for (int i = 0; i < 8; i++)
        *(uint4*)(dst + (i >> 1) * 1024 + (i & 1) * 256) = make_uint4(v[4 * i], v[4 * i + 1], v[4 * i + 2], v[4 * i + 3]);
      if (lane < 2) st_async(mapa(sb + OFF_SCALE + (8 * rank + warp) * 4, lane), min(max(e + smem[OFF_EX + warp] - 124, 1), 254) << 23, mapa(BAR(B_Y), lane));
      fence_async();
      bar_sync(1 + wg);
    }
    if (elect) STAMP(wg, 5);
    {
      const uint32_t dfl = s16 + (OFF_F2F >> 4) + (8 << 16), dil = s16 + (OFF_F2I >> 4) + (8 << 16), d4l = s16 + (OFF_F4 >> 4) + (8 << 16);
      const uint32_t xl = s16 + (OFF_XT >> 4) + 4 * wg * (XT_STRIDE >> 4) + (8 << 16);
      const uint32_t hl = s16 + (OFF_H >> 4) + wg * 512 + (8 << 16);
      uint32_t vst = sb + wg * 8192 + w * 512 + lane * 16, vld = sb + wg * 8192 + w * 2048 + lane * 16;
      uint32_t ya = mapa(sb + OFF_XT + 4 * wg * XT_STRIDE + (2 * rank + (w & 1)) * 1024 + lane * 16, w >> 1);
      const uint32_t ybar = mapa(BAR(B_Y), w >> 1);
      asm volatile("" : "+r"(vst), "+r"(vld), "+r"(ya));
      uint32_t ux[16], uh[16], W[2][8], V0[8], V1[8], y[8], a[4][4];
      uint4* const ot = P.o + ((2 * mb + wg) * 16 + hq) * 1024 + (16 * w + g) * 8 + ((4 * rank + q) ^ g);
#define YOUT(i) do { if ((w >> 1) == rank) { \
          asm volatile("st.shared.v4.b32 [%0], {%1,%2,%3,%4};" ::"r"(ya + (i) * XT_STRIDE), "r"(y[0]), "r"(y[2]), "r"(y[4]), "r"(y[6]) : "memory"); \
          asm volatile("st.shared.v4.b32 [%0], {%1,%2,%3,%4};" ::"r"(ya + (i) * XT_STRIDE + 512), "r"(y[1]), "r"(y[3]), "r"(y[5]), "r"(y[7]) : "memory"); \
        } else { \
          mbar_wait(BAR(B_XFREE + 4 * wg + (i)), 0); \
          st_async4(ya + (i) * XT_STRIDE, y[0], y[2], y[4], y[6], ybar); \
          st_async4(ya + (i) * XT_STRIDE + 512, y[1], y[3], y[5], y[7], ybar); } } while (0)
      auto ocalc = [&](const int hh) {
        if (hh == 0) {
          if (elect) STAMP(wg, 8);
          mbar_wait(BAR(B_KV), 0);
          if (elect) STAMP(wg, 9);
        }
        float oa[2][20];
        wg_fence();
#pragma unroll
        for (int m = 0; m < 4; m++) {
          const uint32_t* p = &pq[m & 1][8 * hh + 4 * (m >> 1)];
          wgmma_rs_n40<1>(oa[m & 1], p[0], p[1], p[2], p[3], dsc(s16 + (OFF_KVB >> 4) + hh * 160 + (m >> 1) * 16 + (8 << 16), 32), m >> 1);
        }
        wg_commit();
        wg_wait<0>();
#pragma unroll
        for (int mt = 0; mt < 2; mt++) {
          float (&o)[20] = oa[mt];
          keep(o);
          const uint32_t den = hadd(pk2(o[16], o[18]), 0x35863586u);
#pragma unroll
          for (int r = 0; r < 2; r++) {
            const float ri = rcp_fast(__uint_as_float(r ? (den & 0xFFFF0000u) : (den << 16)));
            uint4 u;
            u.x = pk2(o[2 * r] * ri, o[2 * r + 1] * ri);
            u.y = pk2(o[4 + 2 * r] * ri, o[5 + 2 * r] * ri);
            u.z = pk2(o[8 + 2 * r] * ri, o[9 + 2 * r] * ri);
            u.w = pk2(o[12 + 2 * r] * ri, o[13 + 2 * r] * ri);
            st_cg4(ot + hh * 8 * 1024 + (64 * mt + 8 * r) * 8, u);
          }
        }
        __syncwarp();
        if (lane == 0) mbar_arrive(BAR(hh ? B_ODONE1 : B_ODONE));
        if (hh == 0 && elect) STAMP(wg, 10);
      };
      uint32_t X[4][2][8], H[4][2][8];
      conv_m1(K, ux, xl);
      conv_m1(K, uh, hl);
      wg_wait<1>(); keepu(ux);
      if (lane == 0) mbar_arrive_cl(BAR(B_XFREE + 4 * wg), rank ^ 1);
      conv_s2(K, ux, X[0], dfl);
      wg_wait<1>(); keepu(uh);
      conv_s2(K, uh, H[0], dfl);
#pragma unroll
      for (int i = 0; i < 4; i++) {
        const bool nx = i < 3;
        const int n = nx ? i + 1 : i;
        const uint32_t vo = (i & 1) ? OFF_H + (i >> 1) * 16384 : OFF_VP;
        if (2 * i == OCH) ocalc(0);
        if (2 * i == OCH + O1D) ocalc(1);
        if (nx) {
          conv_m1(K, ux, xl + n * (XT_STRIDE >> 4));
          conv_m1(K, uh, hl + (n >> 1) * 1024 + (n & 1) * 256);
        }
        if (2 * i != OCH && 2 * i != OCH + O1D) { if (nx) { if (i > 0) wg_wait<3>(); else wg_wait<2>(); } else wg_wait<1>(); }
        keepu(X[i][0]); keepu(X[i][1]); keepu(H[i][0]); keepu(H[i][1]);
        conv_win(K, X[i], W);
        conv_pw<0>(W, H[i], V0, dil);
        conv_pw<1>(W, H[i], V1, dil);
        wg_wait<2>();
        if (i > 0) { keepu(y); YOUT(i - 1); }
        if (2 * i + 1 == OCH) ocalc(0);
        if (2 * i + 1 == OCH + O1D) ocalc(1);
        if (nx) {
          keepu(ux); keepu(uh);
          if (lane == 0) mbar_arrive_cl(BAR(B_XFREE + 4 * wg + n), rank ^ 1);
          conv_s2(K, ux, X[n], dfl);
          wg_wait<1>();
        } else wg_wait<0>();
        keepu(V0); keepu(V1);
        conv_it<0>(K, V0, vst + vo);
        conv_it<1>(K, V1, vst + vo);
        bar_sync(1 + wg);
#pragma unroll
        for (int s = 0; s < 4; s++) ldsm4t(a[s], vld + vo + s * 512);
        if (nx) conv_s2(K, uh, H[n], dfl);
        conv_m4(y, a, d4l);
        if (i > 0 && lane < 2) mbar_arrive_cl(BAR(B_AFREE + i - 1), lane);
        if (elect && i < 3) STAMP(wg, i < 2 ? 6 + i : 9 + i);
      }
      wg_wait<0>(); keepu(y);
      YOUT(3);
      __syncwarp();
      if (lane == 0) mbar_arrive(BAR(B_Y));
      if (elect) STAMP(wg, 12);
    }
    {
      float acc[64];
#pragma unroll 1
      for (int kb = 0; kb < 16; kb++) {
        mbar_wait(BAR(B_FULL2 + kb), 0);
        if (kb == 0 && elect) { STAMP(wg, 13); GSTAMP(wg, 28); }
        const uint32_t da = s16 + ((uint32_t)(SLOT_A >> (4 * kb)) & 15) * 1024 + wg * 512 + (1 << 16);
        const uint32_t db = s16 + ((uint32_t)(SLOT_B >> (4 * kb)) & 15) * 1024 + (512 << 16);
        if (kb == HOLD2 && wg == 0) asm volatile("bar.sync 3, 256;" ::: "memory");
        wg_fence();
#pragma unroll
        for (int ks = 0; ks < 4; ks++) wgmma_ss_n128<0, 1>(acc, dsc(da + ks * 2, SW128), dsc(db + ks * 128, SW128), (kb | ks) != 0);
        wg_commit();
        if (HOLD2 < 16 && kb == 15 && wg == 1) asm volatile("bar.arrive 3, 256;" ::: "memory");
        wg_wait<1>();
        if (kb > 0 && kb < 13 && t < 2 && (kb <= 11 || t == rank)) mbar_arrive_cl(BAR(B_CONS2 + kb - 1), t);
      }
      wg_wait<0>();
      keep(acc);
      if (elect) { STAMP(wg, 14); GSTAMP(wg, 29); }
      mbar_wait(BAR(B_CONS2 + 11), 0);
      const uint32_t stg = sb + ((uint32_t)((wg ? SLOT_A : SLOT_B) >> 44) & 15) * 16384;
      const uint32_t lrow = stg + (16 * w + 8 * ((lane >> 3) & 1) + (lane & 7)) * 128 + (((lane >> 4) ^ (lane & 7)) << 4);
#pragma unroll
      for (int cp = 0; cp < 8; cp++) {
        const float* a = &acc[8 * cp];
        stsm4((lrow ^ ((cp & 3) * 32)) + (cp >> 2) * 8192, pk2(a[0], a[1]), pk2(a[2], a[3]), pk2(a[4], a[5]), pk2(a[6], a[7]));
      }
      fence_async();
      bar_sync(1 + wg);
      if (elect) {
        const int col = 1024 + 256 * cb + 128 * rank, row = 128 * rb + 64 * wg;
        tma2d_st(&P.tmOB, stg, col, row);
        tma2d_st(&P.tmOB, stg + 8192, col + 64, row);
        asm volatile("cp.async.bulk.commit_group;\ncp.async.bulk.wait_group.read 0;" ::: "memory");
        STAMP(wg, 15); GSTAMP(wg, 31); PDUMP(wg);
      }
    }
  } else {
    asm volatile("setmaxnreg.dec.sync.aligned.u32 56;");
    if (warp == 8) {
      if (lane == 0) STAMP(3, 20);
      int st = 1, ph = 1;
      const uint8_t* pfx = (const uint8_t*)P.x + (mb * 256 + hp * 16 + (lane & 15)) * 2048;
      const uint8_t* pfw = (const uint8_t*)P.w + (mb * 8 + (lane & 7)) * 6144 + (lane >> 3) * 2048 + hp * 128;
#pragma unroll 1
      for (int kb = 1; kb < 16; kb++) {
        if (kb >= 3) mbar_wait(BAR(B_EMPTY1 + st), ph);
        const uint32_t sa = sb + st * STAGE_BYTES;
        if (elect_one()) {
          mbar_expect(BAR(B_FULL1 + st), STAGE_BYTES);
          tma2d_mc(sa + rank * 16384, &P.tmX, kb * 64, mb * 256 + rank * 128, BAR(B_FULL1 + st));
          tma3d(sa + 32768, &P.tmW, hp * 64, kb * 64, 0, BAR(B_FULL1 + st));
        }
        if (kb == 1 && lane == 0) STAMP(2, 24);
        if (PFD && kb >= 2) {
#pragma unroll 1
          for (int j = kb == 2 ? 3 : kb + PFD; j <= kb + PFD && j < 16; j++) {
            if (lane < 16) asm volatile("prefetch.global.L2 [%0];" ::"l"(pfx + j * 128));
            if (lane < 24) asm volatile("prefetch.global.L2 [%0];" ::"l"(pfw + j * (64 * 6144)));
          }
          if (kb >= QPF && kb < QPF + 8) asm volatile("prefetch.global.L2 [%0];" ::"l"((const uint8_t*)P.q + (blockIdx.x * 256 + (kb - QPF) * 32 + lane) * 128));
          if (kb >= 4)
            asm volatile("prefetch.global.L2 [%0];" ::"l"(kb < 12 ? (const uint8_t*)P.h + (blockIdx.x * 256 + (kb - 4) * 32 + lane) * 128
                                                                  : (const uint8_t*)P.wo + (blockIdx.x * 128 + (kb - 12) * 32 + lane) * 128));
        }
        if (++st == 3) { st = 0; ph ^= 1; }
      }
      if (lane == 0) STAMP(2, 1);
      const unsigned epoch = P.epoch[blockIdx.x];
#define SLOT(tab, kb) (sb + ((uint32_t)((tab) >> (4 * (kb))) & 15) * 16384)
#define LOAD_B(kb) tma4d(SLOT(SLOT_B, kb), &P.tmWo, 0, ((kb) >> 3) * 32, 2 * ((kb) & 7), 4 * cb + 2 * rank, BAR(B_FULL2 + (kb)))
#define LOAD_A(kb) bulk_ld_mc(SLOT(SLOT_A, kb) + rank * 8192, P.o + (rb * 16 + (kb)) * 1024 + rank * 512, 8192, BAR(B_FULL2 + (kb)))
      mbar_wait(BAR(B_EMPTY1 + 0), 1);
      {
        const uint32_t c0 = clock();
#pragma unroll 1
        for (int i = 0; i < 14; i++) {
          const int kb = i >> 1;
          if (i == 8) mbar_wait(BAR(B_PKFREE), 0);
          while (__any_sync(~0u, (uint32_t)clock() - c0 < i * BPACE)) __nanosleep(32);
          if (elect_one()) {
            if (!(i & 1)) mbar_expect(BAR(B_FULL2 + kb), 16384);
            tma4d(SLOT(SLOT_B, kb) + (i & 1) * 8192, &P.tmWo1, 0, 0, 2 * kb, 4 * cb + 2 * rank + (i & 1), BAR(B_FULL2 + kb));
            if (i == 0) mbar_expect(BAR(B_Q), 8192);
            if (i < 4) tma3d(sb + OFF_SPARE + 2048 * i, &P.tmQ, 16 * cl, 64 * rank + 32 * (i >> 1), 2 * ((i + 6) & 7), BAR(B_Q));
          }
        }
      }
      if (lane == 0) STAMP(2, 2);
      mbar_wait(BAR(B_AFREE), 0);
      if (elect_one()) mbar_expect(BAR(B_FULL2), 16384);
      {
        const uint32_t dst = SLOT(SLOT_A, 0) + rank * 8192;
        const uint4* src = P.o + rb * 16 * 1024 + rank * 512;
        poll_ge(&P.ocnt[rb * 32], 16 * (epoch + 1));
        asm volatile("fence.proxy.async.global;" ::: "memory");
        if (lane == 0) STAMP(2, 3);
        if (elect_one()) bulk_ld_mc(dst, src, 8192, BAR(B_FULL2));
        if (lane == 0) STAMP(3, 23);
      }
#pragma unroll 1
      for (int kb = 1; kb < 7; kb++) {
        mbar_wait(BAR(kb < 3 ? B_AFREE + kb : B_CONS2 + ((kb - 3) >> 1)), 0);
        if (elect_one()) { mbar_expect(BAR(B_FULL2 + kb), 16384); LOAD_A(kb); }
      }
#pragma unroll 1
      for (int kb = 7; kb < 16; kb++) {
        mbar_wait(BAR(B_CONS2 + kb - 5), 0);
        if (kb == 8) mbar_wait(BAR(B_O1RDY), 0);
        if (elect_one()) { mbar_expect(BAR(B_FULL2 + kb), 32768); LOAD_A(kb); LOAD_B(kb); }
      }
      if (lane == 0) { P.epoch[blockIdx.x] = epoch + 1; STAMP(2, 5); PDUMP(2); }
    } else {
      const uint32_t clk0 = clock();
      const int hw = warp - 9, g = lane >> 2, q = lane & 3;
      const unsigned epoch = P.epoch[blockIdx.x];
      const uint32_t tag = ~epoch & 1;
      const uint32_t stg = sb + OFF_STG + hw * STG_STRIDE, sbar = BAR(B_STG + 2 * hw);
      int ph = 0;
      {
        uint32_t tap[2][4];
#pragma unroll
        for (int cg = 0; cg < 2; cg++) {
          const uint2 u = __ldg((const uint2*)(P.shift_k + (16 * cl + 8 * cg + g) * 4));
          tap[cg][0] = __byte_perm(u.x, 0, 0x1010); tap[cg][1] = __byte_perm(u.x, 0, 0x3232);
          tap[cg][2] = __byte_perm(u.y, 0, 0x1010); tap[cg][3] = __byte_perm(u.y, 0, 0x3232);
        }
        if (hw == 0 && lane < 8) *(float*)(smem + OFF_D + 4 * lane) = __bfloat162float(P.D[blockIdx.x * 8 + lane]);
        if (hw == 1) asm volatile("prefetch.global.L2 [%0];" ::"l"(P.thr + (lane + 32 * (blockIdx.x & 1)) * 32));
        if (hw == 0 && elect_one()) {
          *(volatile unsigned*)(smem + OFF_EPOCH) = epoch;
          mbar_expect(BAR(B_XRAW), 16384);
          mbar_expect(BAR(B_Y), 16384 + 64);
        }
        for (int i = hw * 32 + lane; i < 528; i += 96) st_tag4(P.part + (hp * 8 + mb) * 2176 + 4 * i, 0.f, 0.f, 0.f, 0.f, tag ^ 1);
        if (hw < 2 || lane < 2) st_tag4(P.kv + hp * 2176 + (4 * (hw < 2 ? 64 * mb + 32 * hw + lane : 512 + 2 * mb + lane)), 0.f, 0.f, 0.f, 0.f, tag ^ 1);
        if (lane == 0) STAMP(3, hw);
        const uint32_t xo = sb + OFF_XT + g * XT_STRIDE + rank * 2048 + q * 4;
        const int krow = 8 + (lane & 7) - (lane >> 3);
        const uint32_t ka = stg + krow * 32 + ((krow & 4) << 2), va = stg + 2304 + lane * 32 + ((lane & 4) << 2);
        int b = 0;
#pragma unroll 1
        for (int ci = hw - 3; ci < 16; ci += 3) {
          const uint32_t bo = b ? OFF_F2F - OFF_STG : 0, bn = b ? 0 : OFF_F2F - OFF_STG;
          if (ci + 3 < 16) {
            while (__any_sync(~0u, (uint32_t)clock() - clk0 < HSTART + (ci + 3) * PACE)) __nanosleep(64);
            if (elect_one()) {
              mbar_expect(sbar + 8 * (b ^ 1), 2304 + 2048);
              tma2d(stg + bn, &P.tmK, 16 * cl, 1024 * rank + 64 * (ci + 3) - 8, sbar + 8 * (b ^ 1));
              tma2d(stg + bn + 2304, &P.tmV, 16 * cl, 1024 * rank + 64 * (ci + 3), sbar + 8 * (b ^ 1));
            }
          }
          if (ci >= 0) {
            mbar_wait(sbar + 8 * b, (ph >> b) & 1);
            ph ^= 1 << b;
#pragma unroll 1
            for (int grp = 0; grp < 2; grp++) {
#pragma unroll
              for (int cg = 0; cg < 2; cg++) {
                const uint32_t dst = mapa(xo + (ci >> 3) * 1024 + ((ci & 7) * 4 + 2 * grp) * 16, cg), xbar = mapa(BAR(B_XRAW), cg);
                uint32_t vv[4], kk[4][4];
                ldsm4t(vv, (va ^ (cg * 16)) + bo + grp * 1024);
#pragma unroll
                for (int rg = 0; rg < 4; rg++) ldsm4t(kk[rg], (ka ^ (cg * 16)) + bo + grp * 1024 + rg * 256);
#pragma unroll
                for (int rg = 0; rg < 4; rg++)
                  vv[rg] = hmul(hadd(hadd(hadd(hmul(kk[rg][3], tap[cg][3]), hmul(kk[rg][2], tap[cg][2])), hmul(kk[rg][1], tap[cg][1])), hmul(kk[rg][0], tap[cg][0])), vv[rg]);
                if (cg == rank) {
#pragma unroll
                  for (int rg = 0; rg < 4; rg++) asm volatile("st.shared.b32 [%0], %1;" ::"r"(dst + (rg & 1) * 512 + (rg >> 1) * 16), "r"(vv[rg]) : "memory");
                } else {
#pragma unroll
                  for (int rg = 0; rg < 4; rg++) st_async(dst + (rg & 1) * 512 + (rg >> 1) * 16, vv[rg], xbar);
                }
              }
            }
          }
          b ^= 1;
        }
      }
      if (lane == 0) STAMP(3, 3 + hw);
      asm volatile("bar.sync 4, 96;" ::: "memory");
      if (hw == 0 && elect_one()) { mbar_expect(BAR(B_XT), 10240); bulk_ld(sb + OFF_F2F, P.img, 10240, BAR(B_XT)); }
      mbar_wait(BAR(B_XRAW), 0);
#pragma unroll 1
      for (int c = hw; c < 8; c += 3) {
        uint4* p = (uint4*)(smem + OFF_XT + c * XT_STRIDE) + lane;
        uint32_t v[32];
#pragma unroll
        for (int i = 0; i < 8; i++) { const uint4 u = p[i * 32]; v[4 * i] = u.x; v[4 * i + 1] = u.y; v[4 * i + 2] = u.z; v[4 * i + 3] = u.w; }
        const int e = normalise(v, 0.f);
#pragma unroll
        for (int i = 0; i < 8; i++) p[i * 32] = make_uint4(v[4 * i], v[4 * i + 1], v[4 * i + 2], v[4 * i + 3]);
        if (lane == 0) smem[OFF_EX + c] = e;
        if (c < 6 && elect_one()) {
          if (c < 3) mbar_expect(sbar, 4096);
          tma3d(sb + OFF_STG + 2048 * c, &P.tmQ, 16 * cl, 64 * rank, 2 * c, sbar);
        }
      }
      fence_async();
      __syncwarp();
      if (lane == 0) { mbar_arrive(BAR(B_XT)); STAMP(3, 13 + hw); }
      mbar_wait(BAR(B_PKFREE), 0);
      if (hw == 0 && lane == 0) STAMP(3, 19);
      if (PD1) __nanosleep(PD1);
      {
        const int pi = hw < 2 ? 64 * mb + 32 * hw + lane : 512 + 2 * mb + (lane & 1);
        const float* psrc = P.part + hp * 8 * 2176 + 4 * pi;
        uint4 f[8];
#pragma unroll
        for (int p = 0; p < 8; p++) f[p] = ld_rlx4(psrc + p * 2176);
        if (!opaque_true()) __trap();
#pragma unroll 1
        for (int n = 0; __any_sync(~0u, stale8(f, tag) & 1); n++) {
#pragma unroll
          for (int p = 0; p < 8; p++) ld_stale4(f[p], psrc + p * 2176, tag);
          if (n > SPIN_LIMIT) __trap();
        }
        float s0 = 0.f, s1 = 0.f, s2 = 0.f, s3 = 0.f;
#pragma unroll
        for (int p = 0; p < 8; p++) { s0 += __uint_as_float(f[p].x); s1 += __uint_as_float(f[p].y); s2 += __uint_as_float(f[p].z); s3 += __uint_as_float(f[p].w); }
        if (hw < 2 || lane < 2) st_tag4(P.kv + hp * 2176 + (4 * pi), s0, s1, s2, s3, tag);
      }
      if (lane == 0 && hw == 0) STAMP(3, 8);
      if (hw == 2) {
        unsigned* cnt = P.ocnt + (2 * mb + lane) * 32;
#pragma unroll 1
        for (int hh = 0; hh < 2; hh++) {
          mbar_wait(BAR(hh ? B_ODONE1 : B_ODONE), 0);
          if (lane < 2) asm volatile("red.release.gpu.global.add.u32 [%0], 1;" ::"l"(cnt + hh * 512) : "memory");
          if (lane == 0) STAMP(3, hh ? 6 : 7);
        }
        poll_ge(&P.ocnt[512 + rb * 32], 16 * (epoch + 1));
        asm volatile("fence.proxy.async.global;" ::: "memory");
        if (lane == 0) { mbar_arrive(BAR(B_O1RDY)); STAMP(2, 4); }
        __syncwarp();
      } else {
        if (PD2) __nanosleep(PD2);
        const int t = hw * 32 + lane;
        uint4 f[8];
        const float* src = P.kv + hp * 2176 + (4 * t);
        const float* zsrc = P.kv + hp * 2176 + (2048 + (t & 48) + 2 * (lane & 6));
        uint4 zp = ld_rlx4(zsrc);
#pragma unroll
        for (int p = 0; p < 8; p++) f[p] = ld_rlx4(src + 4 * ((p & 3) * 128 + (p >> 2) * 64));
        if (!opaque_true()) __trap();
#pragma unroll 1
        for (int n = 0; __any_sync(~0u, (stale8(f, tag) | (zp.x ^ tag)) & 1); n++) {
          ld_stale4(zp, zsrc, tag);
#pragma unroll
          for (int p = 0; p < 8; p++) ld_stale4(f[p], src + 4 * ((p & 3) * 128 + (p >> 2) * 64), tag);
          if (n > SPIN_LIMIT) __trap();
        }
#define PK2U(a, b) pk2(__uint_as_float(a), __uint_as_float(b))
#pragma unroll
        for (int hh = 0; hh < 2; hh++) {
          const uint4* ff = &f[4 * hh];
          uint8_t* dst = smem + OFF_KVB + hh * 2560 + q * 512 + (16 * hw + g) * 16;
          *(uint4*)dst = make_uint4(PK2U(ff[0].x, ff[0].y), PK2U(ff[1].x, ff[1].y), PK2U(ff[2].x, ff[2].y), PK2U(ff[3].x, ff[3].y));
          *(uint4*)(dst + 128) = make_uint4(PK2U(ff[0].z, ff[0].w), PK2U(ff[1].z, ff[1].w), PK2U(ff[2].z, ff[2].w), PK2U(ff[3].z, ff[3].w));
        }
        const uint32_t zf = (lane & 1) ? ((lane & 8) ? zp.w : zp.z) : ((lane & 8) ? zp.y : zp.x);
        const uint32_t zz = PK2U(zf, zf);
        *(uint4*)(smem + OFF_KVB + hw * 2560 + 2048 + lane * 16) = make_uint4(zz, zz, zz, zz);
        fence_async();
        __syncwarp();
        if (lane == 0) { mbar_arrive(BAR(B_KV)); if (hw == 0) STAMP(3, 9); }
      }
#define QBUF(ci) (sb + 2048 * (ci) + ((ci) < 6 ? OFF_STG : (ci) < 10 ? OFF_SPARE - 6 * 2048 : OFF_F2F - 10 * 2048))
      mbar_wait(BAR(B_Y), 0);
      if (elect_one()) {
        mbar_expect(sbar + 8, 4096);
#pragma unroll 1
        for (int ci = hw ? hw + 9 : 12; ci < 16; ci += 3) tma3d(QBUF(ci), &P.tmQ, 16 * cl, 64 * rank + 32, 2 * (ci & 7), sbar + 8);
      }
      mbar_wait(BAR(B_Q), 0);
      {
        const float2 sc0 = *(const float2*)(smem + OFF_SCALE + 8 * q), sc1 = *(const float2*)(smem + OFF_SCALE + 32 + 8 * q);
        const uint32_t yl = sb + OFF_XT + (lane & 7) * XT_STRIDE + (lane >> 3) * 16;
#pragma unroll 1
        for (int ci = hw; ci < 16; ci += 3) {
          const uint32_t qb = QBUF(ci);
          const int b = ci >= 10;
          mbar_wait(sbar + 8 * b, (ph >> b) & 1);
#pragma unroll 1
          for (int nl = 0; nl < 2; nl++) {
            uint32_t yy[2][4], qq[2][4];
            const uint32_t qa = qb + lane * 32 + ((lane & 4) << 2) + nl * 1024;
#pragma unroll
            for (int cg = 0; cg < 2; cg++) { ldsm4t(yy[cg], yl + cg * 2048 + (2 * ci + nl) * 64); ldsm4(qq[cg], qa ^ (cg * 16)); }
#pragma unroll
            for (int cg = 0; cg < 2; cg++) {
              const float2 sc = cg ? sc1 : sc0;
#pragma unroll
              for (int m = 0; m < 4; m++) {
                const float2 f = __half22float2(*(const __half2*)&yy[cg][m]);
                qq[cg][m] = hmul(qq[cg][m], pk2(f.x * sc.x, f.y * sc.y));
              }
              stsm4(qa ^ (cg * 16), qq[cg][0], qq[cg][1], qq[cg][2], qq[cg][3]);
            }
          }
          fence_async();
          __syncwarp();
          if (elect_one()) tma3d_st(&P.tmOA, qb, 16 * cl, 64 * rank + 32 * (ci >> 3), 2 * (ci & 7));
        }
        asm volatile("cp.async.bulk.commit_group;\ncp.async.bulk.wait_group.read 0;" ::: "memory");
      }
      if (lane == 0) STAMP(3, 10 + hw);
    }
  }
}

typedef CUresult (*EncodeFn)(CUtensorMap*, CUtensorMapDataType, cuuint32_t, void*, const cuuint64_t*, const cuuint64_t*,
                             const cuuint32_t*, const cuuint32_t*, CUtensorMapInterleave, CUtensorMapSwizzle,
                             CUtensorMapL2promotion, CUtensorMapFloatOOBfill);

static void enc(EncodeFn fn, CUtensorMap* m, const void* p, int rank, const cuuint64_t* dims, const cuuint64_t* strides,
                const cuuint32_t* box, CUtensorMapSwizzle swz, CUtensorMapL2promotion promo) {
  cuuint32_t es[4] = {1, 1, 1, 1};
  fn(m, CU_TENSOR_MAP_DATA_TYPE_BFLOAT16, rank, (void*)p, dims, strides, box, es, CU_TENSOR_MAP_INTERLEAVE_NONE, swz, promo,
     CU_TENSOR_MAP_FLOAT_OOB_FILL_NONE);
}

extern "C" void kernel_launch(void* const* d_in, const int* in_sizes, int n_in, void* d_out, int out_size) {
  void* fp = nullptr;
  cudaDriverEntryPointQueryResult qr;
  cudaGetDriverEntryPoint("cuTensorMapEncodeTiled", &fp, cudaEnableDefault, &qr);
  EncodeFn fn = (EncodeFn)fp;
  Params P;
  P.shift_k = (const __nv_bfloat16*)d_in[3]; P.h = (const __nv_bfloat16*)d_in[4]; P.D = (const __nv_bfloat16*)d_in[5];
  P.q = (const __nv_bfloat16*)d_in[0];
  cudaGetSymbolAddress((void**)&P.part, g_part); cudaGetSymbolAddress((void**)&P.kv, g_kv); cudaGetSymbolAddress((void**)&P.o, g_o);
  cudaGetSymbolAddress((void**)&P.ocnt, g_ocnt); cudaGetSymbolAddress((void**)&P.epoch, g_epoch);
  cudaGetSymbolAddress((void**)&P.thr, c_thr); cudaGetSymbolAddress((void**)&P.img, c_img);
  P.x = (const __nv_bfloat16*)d_in[6]; P.w = (const __nv_bfloat16*)d_in[7]; P.wo = (const __nv_bfloat16*)d_in[8];
  const CUtensorMapSwizzle S128 = CU_TENSOR_MAP_SWIZZLE_128B, S32 = CU_TENSOR_MAP_SWIZZLE_32B;
  const CUtensorMapL2promotion P0 = CU_TENSOR_MAP_L2_PROMOTION_NONE, P128 = CU_TENSOR_MAP_L2_PROMOTION_L2_128B;
  { cuuint64_t d[2] = {1024, 2048}, s[1] = {2048}; cuuint32_t b[2] = {64, 128}; enc(fn, &P.tmX, d_in[6], 2, d, s, b, S128, P128); }
  { cuuint64_t d[3] = {1024, 1024, 3}, s[2] = {6144, 2048}; cuuint32_t b[3] = {64, 64, 3}; enc(fn, &P.tmW, d_in[7], 3, d, s, b, S128, P128); }
  { cuuint64_t d[4] = {64, 64, 16, 16}, s[3] = {2048, 131072, 128}; cuuint32_t b[4] = {64, 32, 2, 2}; enc(fn, &P.tmWo, d_in[8], 4, d, s, b, S128, P128); }
  { cuuint64_t d[4] = {64, 64, 16, 16}, s[3] = {2048, 131072, 128}; cuuint32_t b[4] = {64, 32, 2, 1}; enc(fn, &P.tmWo1, d_in[8], 4, d, s, b, S128, P128); }
  { cuuint64_t d[2] = {1024, 2048}, s[1] = {2048}; cuuint32_t b[2] = {16, 72}; enc(fn, &P.tmK, d_in[1], 2, d, s, b, S32, PKV); }
  { cuuint64_t d[2] = {1024, 2048}, s[1] = {2048}; cuuint32_t b[2] = {16, 64}; enc(fn, &P.tmV, d_in[2], 2, d, s, b, S32, PKV); }
  { cuuint64_t d[3] = {1024, 128, 16}, s[2] = {32768, 2048}; cuuint32_t b[3] = {16, 32, 2}; enc(fn, &P.tmQ, d_in[0], 3, d, s, b, S32, PKV); }
  { cuuint64_t d[3] = {1024, 128, 16}, s[2] = {65536, 4096}; cuuint32_t b[3] = {16, 32, 2}; enc(fn, &P.tmOA, d_out, 3, d, s, b, S32, P0); }
  { cuuint64_t d[2] = {2048, 2048}, s[1] = {4096}; cuuint32_t b[2] = {64, 64}; enc(fn, &P.tmOB, d_out, 2, d, s, b, S128, P0); }
  cudaFuncSetAttribute(fused_kernel, cudaFuncAttributeMaxDynamicSharedMemorySize, SMEM_TOTAL);
  fused_kernel<<<128, 384, SMEM_TOTAL>>>(P);
}
```

```cpp
#include <cuda_runtime.h>
#include <cuda_bf16.h>
#include <cuda_fp16.h>
#include <cuda.h>
#include <stdint.h>

template<int TA, int TB, int SA=1> __device__ __forceinline__ void wgmma_ss_n192(float (&d)[96], uint64_t da, uint64_t db, int scale_d) {
  asm volatile("{\n.reg .pred p;\nsetp.ne.b32 p, %98, 0;\n"
    "wgmma.mma_async.sync.aligned.m64n192k16.f32.bf16.bf16 {%0, %1, %2, %3, %4, %5, %6, %7, %8, %9, %10, %11, %12, %13, %14, %15, %16, %17, %18, %19, %20, %21, %22, %23, %24, %25, %26, %27, %28, %29, %30, %31, %32, %33, %34, %35, %36, %37, %38, %39, %40, %41, %42, %43, %44, %45, %46, %47, %48, %49, %50, %51, %52, %53, %54, %55, %56, %57, %58, %59, %60, %61, %62, %63, %64, %65, %66, %67, %68, %69, %70, %71, %72, %73, %74, %75, %76, %77, %78, %79, %80, %81, %82, %83, %84, %85, %86, %87, %88, %89, %90, %91, %92, %93, %94, %95}, %96, %97, p, %101, 1, %99, %100;\n}\n"
    : "+f"(d[0]), "+f"(d[1]), "+f"(d[2]), "+f"(d[3]), "+f"(d[4]), "+f"(d[5]), "+f"(d[6]), "+f"(d[7]), "+f"(d[8]), "+f"(d[9]), "+f"(d[10]), "+f"(d[11]), "+f"(d[12]), "+f"(d[13]), "+f"(d[14]), "+f"(d[15]), "+f"(d[16]), "+f"(d[17]), "+f"(d[18]), "+f"(d[19]), "+f"(d[20]), "+f"(d[21]), "+f"(d[22]), "+f"(d[23]), "+f"(d[24]), "+f"(d[25]), "+f"(d[26]), "+f"(d[27]), "+f"(d[28]), "+f"(d[29]), "+f"(d[30]), "+f"(d[31]), "+f"(d[32]), "+f"(d[33]), "+f"(d[34]), "+f"(d[35]), "+f"(d[36]), "+f"(d[37]), "+f"(d[38]), "+f"(d[39]), "+f"(d[40]), "+f"(d[41]), "+f"(d[42]), "+f"(d[43]), "+f"(d[44]), "+f"(d[45]), "+f"(d[46]), "+f"(d[47]), "+f"(d[48]), "+f"(d[49]), "+f"(d[50]), "+f"(d[51]), "+f"(d[52]), "+f"(d[53]), "+f"(d[54]), "+f"(d[55]), "+f"(d[56]), "+f"(d[57]), "+f"(d[58]), "+f"(d[59]), "+f"(d[60]), "+f"(d[61]), "+f"(d[62]), "+f"(d[63]), "+f"(d[64]), "+f"(d[65]), "+f"(d[66]), "+f"(d[67]), "+f"(d[68]), "+f"(d[69]), "+f"(d[70]), "+f"(d[71]), "+f"(d[72]), "+f"(d[73]), "+f"(d[74]), "+f"(d[75]), "+f"(d[76]), "+f"(d[77]), "+f"(d[78]), "+f"(d[79]), "+f"(d[80]), "+f"(d[81]), "+f"(d[82]), "+f"(d[83]), "+f"(d[84]), "+f"(d[85]), "+f"(d[86]), "+f"(d[87]), "+f"(d[88]), "+f"(d[89]), "+f"(d[90]), "+f"(d[91]), "+f"(d[92]), "+f"(d[93]), "+f"(d[94]), "+f"(d[95])
    : "l"(da), "l"(db), "r"(scale_d), "n"(TA), "n"(TB), "n"(SA));
}
template<int TA, int TB, int SA=1> __device__ __forceinline__ void wgmma_ss_n128(float (&d)[64], uint64_t da, uint64_t db, int scale_d) {
  asm volatile("{\n.reg .pred p;\nsetp.ne.b32 p, %66, 0;\n"
    "wgmma.mma_async.sync.aligned.m64n128k16.f32.bf16.bf16 {%0, %1, %2, %3, %4, %5, %6, %7, %8, %9, %10, %11, %12, %13, %14, %15, %16, %17, %18, %19, %20, %21, %22, %23, %24, %25, %26, %27, %28, %29, %30, %31, %32, %33, %34, %35, %36, %37, %38, %39, %40, %41, %42, %43, %44, %45, %46, %47, %48, %49, %50, %51, %52, %53, %54, %55, %56, %57, %58, %59, %60, %61, %62, %63}, %64, %65, p, %69, 1, %67, %68;\n}\n"
    : "+f"(d[0]), "+f"(d[1]), "+f"(d[2]), "+f"(d[3]), "+f"(d[4]), "+f"(d[5]), "+f"(d[6]), "+f"(d[7]), "+f"(d[8]), "+f"(d[9]), "+f"(d[10]), "+f"(d[11]), "+f"(d[12]), "+f"(d[13]), "+f"(d[14]), "+f"(d[15]), "+f"(d[16]), "+f"(d[17]), "+f"(d[18]), "+f"(d[19]), "+f"(d[20]), "+f"(d[21]), "+f"(d[22]), "+f"(d[23]), "+f"(d[24]), "+f"(d[25]), "+f"(d[26]), "+f"(d[27]), "+f"(d[28]), "+f"(d[29]), "+f"(d[30]), "+f"(d[31]), "+f"(d[32]), "+f"(d[33]), "+f"(d[34]), "+f"(d[35]), "+f"(d[36]), "+f"(d[37]), "+f"(d[38]), "+f"(d[39]), "+f"(d[40]), "+f"(d[41]), "+f"(d[42]), "+f"(d[43]), "+f"(d[44]), "+f"(d[45]), "+f"(d[46]), "+f"(d[47]), "+f"(d[48]), "+f"(d[49]), "+f"(d[50]), "+f"(d[51]), "+f"(d[52]), "+f"(d[53]), "+f"(d[54]), "+f"(d[55]), "+f"(d[56]), "+f"(d[57]), "+f"(d[58]), "+f"(d[59]), "+f"(d[60]), "+f"(d[61]), "+f"(d[62]), "+f"(d[63])
    : "l"(da), "l"(db), "r"(scale_d), "n"(TA), "n"(TB), "n"(SA));
}
template<int TA, int TB, int SA=1> __device__ __forceinline__ void wgmma_ss_n72(float (&d)[36], uint64_t da, uint64_t db, int scale_d) {
  asm volatile("{\n.reg .pred p;\nsetp.ne.b32 p, %38, 0;\n"
    "wgmma.mma_async.sync.aligned.m64n72k16.f32.bf16.bf16 {%0, %1, %2, %3, %4, %5, %6, %7, %8, %9, %10, %11, %12, %13, %14, %15, %16, %17, %18, %19, %20, %21, %22, %23, %24, %25, %26, %27, %28, %29, %30, %31, %32, %33, %34, %35}, %36, %37, p, %41, 1, %39, %40;\n}\n"
    : "+f"(d[0]), "+f"(d[1]), "+f"(d[2]), "+f"(d[3]), "+f"(d[4]), "+f"(d[5]), "+f"(d[6]), "+f"(d[7]), "+f"(d[8]), "+f"(d[9]), "+f"(d[10]), "+f"(d[11]), "+f"(d[12]), "+f"(d[13]), "+f"(d[14]), "+f"(d[15]), "+f"(d[16]), "+f"(d[17]), "+f"(d[18]), "+f"(d[19]), "+f"(d[20]), "+f"(d[21]), "+f"(d[22]), "+f"(d[23]), "+f"(d[24]), "+f"(d[25]), "+f"(d[26]), "+f"(d[27]), "+f"(d[28]), "+f"(d[29]), "+f"(d[30]), "+f"(d[31]), "+f"(d[32]), "+f"(d[33]), "+f"(d[34]), "+f"(d[35])
    : "l"(da), "l"(db), "r"(scale_d), "n"(TA), "n"(TB), "n"(SA));
}
template<int TB, int SA=1> __device__ __forceinline__ void wgmma_rs_n40(float (&d)[20], uint32_t a0, uint32_t a1, uint32_t a2, uint32_t a3, uint64_t db, int scale_d) {
  asm volatile("{\n.reg .pred p;\nsetp.ne.b32 p, %25, 0;\n"
    "wgmma.mma_async.sync.aligned.m64n40k16.f32.bf16.bf16 {%0, %1, %2, %3, %4, %5, %6, %7, %8, %9, %10, %11, %12, %13, %14, %15, %16, %17, %18, %19}, {%20, %21, %22, %23}, %24, p, %27, 1, %26;\n}\n"
    : "+f"(d[0]), "+f"(d[1]), "+f"(d[2]), "+f"(d[3]), "+f"(d[4]), "+f"(d[5]), "+f"(d[6]), "+f"(d[7]), "+f"(d[8]), "+f"(d[9]), "+f"(d[10]), "+f"(d[11]), "+f"(d[12]), "+f"(d[13]), "+f"(d[14]), "+f"(d[15]), "+f"(d[16]), "+f"(d[17]), "+f"(d[18]), "+f"(d[19])
    : "r"(a0), "r"(a1), "r"(a2), "r"(a3), "l"(db), "r"(scale_d), "n"(TB), "n"(SA));
}
template<int TB> __device__ __forceinline__ void wgmma_hrs_n64(uint32_t (&d)[16], uint32_t a0, uint32_t a1, uint32_t a2, uint32_t a3, uint64_t db, int scale_d) {
  asm volatile("{\n.reg .pred p;\nsetp.ne.b32 p, %21, 0;\n"
    "wgmma.mma_async.sync.aligned.m64n64k16.f16.f16.f16 {%0, %1, %2, %3, %4, %5, %6, %7, %8, %9, %10, %11, %12, %13, %14, %15}, {%16, %17, %18, %19}, %20, p, 1, 1, %22;\n}\n"
    : "+r"(d[0]), "+r"(d[1]), "+r"(d[2]), "+r"(d[3]), "+r"(d[4]), "+r"(d[5]), "+r"(d[6]), "+r"(d[7]), "+r"(d[8]), "+r"(d[9]), "+r"(d[10]), "+r"(d[11]), "+r"(d[12]), "+r"(d[13]), "+r"(d[14]), "+r"(d[15])
    : "r"(a0), "r"(a1), "r"(a2), "r"(a3), "l"(db), "r"(scale_d), "n"(TB));
}
template<int TB> __device__ __forceinline__ void wgmma_hrs_n32(uint32_t (&d)[8], uint32_t a0, uint32_t a1, uint32_t a2, uint32_t a3, uint64_t db, int scale_d) {
  asm volatile("{\n.reg .pred p;\nsetp.ne.b32 p, %13, 0;\n"
    "wgmma.mma_async.sync.aligned.m64n32k16.f16.f16.f16 {%0, %1, %2, %3, %4, %5, %6, %7}, {%8, %9, %10, %11}, %12, p, 1, 1, %14;\n}\n"
    : "+r"(d[0]), "+r"(d[1]), "+r"(d[2]), "+r"(d[3]), "+r"(d[4]), "+r"(d[5]), "+r"(d[6]), "+r"(d[7])
    : "r"(a0), "r"(a1), "r"(a2), "r"(a3), "l"(db), "r"(scale_d), "n"(TB));
}

__device__ __align__(128) const uint32_t c_thr[1536] = {
  0x33fb33ff,0xa49c9de4,0x33273352,0xaf2cae76,0x33e233f1,0xa96ca7bd,0x32c432f7,0xb045afdd,0x33b733cf,0xac3eaaf7,0x3250328c,0xb0eab099,
  0x3378339a,0xadbcacff,0x31cd3211,0xb182b137,0x33d033fb,0xaadea46a,0x299e2d17,0xb3e0b396,0x32fb337a,0xafd2adb1,0xa78b1f76,0xb3f2b3ff,
  0x318b3254,0xb1c5b0e5,0xae6bac32,0xb354b3b8,0x2f4230a3,0xb321b285,0xb133b040,0xb215b2c7,0x337c33f2,0xada5a759,0xb179afc8,0xb1d6b2fe,
  0x31463293,0xb204b08e,0xb394b2ba,0xad23b055,0x2b402f4e,0xb3cbb31e,0xb3e4b3f9,0x293ba533,0xac269c52,0xb3bab400,0xb258b357,0x30e02e5f,
  0x330133e5,0xafbda922,0xb3f3b3c9,0x2727ab59,0x2deb314a,0xb36fb200,0xb194b32f,0x31bc2f0a,0xacdb2084,0xb39fb3ff,0xa565aea4,0x33f93347,
  0xb2b6b0db,0xb05ab25c,0x30892c1a,0x329733bc,0x326033d4,0xb0d6aa94,0xb00ab29b,0x32e83084,0x20e82f64,0xb3feb318,0x2d8da597,0x338133f8,
  0xb1fcae48,0xb14fb35c,0x339031b8,0x2d3a3199,0xb3e6b3ae,0x2909ac7b,0x32d133f4,0xb030a6f5,0x319d33bf,0xb1b3ac02,0x2e3ca874,0x335e33ec,
  0xacc32b89,0xb3a3b3c6,0x33f83276,0x25c930b7,0xb3dcb1f8,0xaa01b154,0x30653335,0xb2b0aef4,0xb107b383,0x32392d81,0xafa6214d,0xb307b3fe,
  0x30bc33a5,0xb273acb7,0x33c5311b,0x2ba23229,0xb0cc94b6,0xb267b400,0x30153360,0xb2e1ae31,0xb385b3ab,0x2d76ac93,0xb166a691,0xb1e7b3f5,
  0x22deb06a,0x33fd32ac,0xb337b3da,0x2ee8aa19,0x2f853387,0xb310ad6a,0x322d33fe,0xb1162216,0xb2a9abd3,0xb06fb3c2,0xb07428a6,0xb2a5b3ea,
  0xb111b3e9,0x323128be,0xb30db3c3,0x2f90abba,0x31aa227a,0x31a633fd,0x2e25ad5e,0x33633389,0x2d6a3365,0xb387ae1a,0xa21631aa,0xb3feb1a6,
  0xb3c2af85,0xabd3b310,0xb3eab22d,0x28a6b116,0xa8beb2a9,0x33e9306f,0x2bbab074,0x33c332a5,0x33fd3111,0x227a3231,0x3389330d,0xad5e2f90,
  0x2a63333f,0xb3d7aec6,0xb2a2a1b1,0xb07ab3fe,0xb3f7b158,0x25fbb1f4,0xacb7b38b,0x33a52d52,0x2e0eb025,0x336832d8,0x340030bc,0x14b63273,
  0x323533c0,0xb10c2beb,0xac9330cc,0xb3abb267,0x23433316,0xb3fdaf6f,0xb38eb225,0x2d46b11f,0xb342b29e,0x2ebbb07f,0x31e3aa7c,0x316b33d6,
  0x3264a6c3,0x30d133f5,0x2c0233ac,0xb3bfac87,0x28f0336a,0xb3e7ae02,0xb3c6b19d,0x2b89b1b3,0xa59732e8,0xb3f8b00a,0xaccfb3ed,0x33a1285b,
  0xb1b8b381,0x3199ad8d,0x336c31df,0xadf73170,0x33f42d3a,0x26f53390,0xb30423a7,0xafb2b3fc,0xb05f3030,0xb2b3b2d1,0x29e8b27a,0x33dd30b2,
  0xab5932b6,0xb3c9b05a,0x30adb089,0x327e3297,0xaf0ab3f3,0x332fa727,0x240633b0,0xb3fcac6f,0x33473194,0xaea431bc,0xb174b359,0x31daae54,
  0xb3bca565,0xac1ab3f9,0x33ee2f59,0xa842331b,0xaddf3281,0xb371b0a8,0x34002b40,0x1c5233cb,0xa759b3ef,0x33f22829,0xb2fe2c26,0xafc8b3ba,
  0x308e337c,0xb2932da5,0x3055b179,0x32ba31d6,0xb31eb146,0x2f4eb204,0xa5333394,0xb3f9ad23,0xaff33249,0xb2f1b0f3,0x30e532fb,0xb2542fd2,
  0x2b28b373,0x33cc2dd4,0xb285b18b,0x30a3b1c5,0x246a33fa,0xb3fba500,0x33962f42,0xad173321,0xadb1b3d0,0x337aaade,0xb3ffa99e,0x1f76b3e0,
  0xb0ee320d,0xb24db13c,0xac4b3398,0xb3b5ad0b,0x304ab289,0x32c1309e,0x2985b3ce,0x33e12b0f,0xaf3732f4,0xb324afe8,0xa4ce33f0,0xb3faa7ef,
  0x2dc8b34f,0x33762e82,0x9de4b3ff,0x33ff1ead,0xb1c931cd,0xb186b182,0xb3762e82,0xadc8b34f,0x324db13c,0x30ee320d,0x33b5ad0b,0x2c4b3398,
  0xb2c1309e,0xb04ab289,0xb3e12b0f,0xa985b3ce,0x3324afe8,0x2f3732f4,0x33faa7ef,0x24ce33f0,0xb285318b,0xb0a3b1c5,0xb2c7ae6b,0x3040b354,
  0x3396af42,0x2d173321,0x31413133,0xb2093215,0xb3ff299e,0x9f76b3e0,0xae8db2bd,0x334cb050,0x33b8278b,0xac3233f2,0x281033b3,0xb3ef2c57,
  0xb31e3146,0xaf4eb204,0xa533b394,0x33f9ad23,0x3400ab40,0x9c5233cb,0xae5f33e4,0xb357a93b,0xb2feac26,0x2fc8b3ba,0x3245b258,0x30f830e0,
  0x30553179,0xb2ba31d6,0xb3df2e99,0xa9b6b34a,0xb39230fd,0xad2fb241,0x3200b301,0x314a2fbd,0x337f1b11,0xad993400,0xb3ff2deb,0xa084b36f,
  0xb005b129,0x32ebb21d,0x325c2cdb,0xb0db339f,0xa92233de,0xb3e529cf,0xab59b2b6,0x33c9b05a,0xb3dd30b2,0xa9e8b27a,0x33d4ab71,0xaa9433c8,
  0x32212c0e,0xb12433bd,0xaf64b0d6,0x3318b260,0x197fb345,0x3400aeaf,0xae4833fe,0xb35c20e8,0xb23d3332,0xb102aeff,0x33aeb14f,0x2c7b31fc,
  0xb3fe3065,0xa14db2b0,0x2ebb307f,0xb342329e,0x300f2fa6,0xb2e53307,0x30d1b3f5,0x326426c3,0x302ab400,0x32d517db,0xb3e72e02,0x28f0b36a,
  0xb3fd2f6f,0x2343b316,0x2d46311f,0xb38e3225,0xb3f53015,0x2691b2e1,0xaf9b33eb,0xb30a288d,0x2a193166,0xb3da31e7,0x33d7aec6,0xaa63333f,
  0x3313b337,0x2f7a2ee8,0xa5fbb1f4,0x33f7b158,0xb1a1a8d7,0x31afb3e8,0xb36832d8,0xae0eb025,0xb3c22f85,0x2bd3b310,0xb3ea322d,0xa8a6b116,
  0xa8be32a9,0xb3e9306f,0x2bba3074,0xb3c332a5,0x33fdb111,0xa27a3231,0x3389b30d,0x2d5e2f90,0xa216b1aa,0x33feb1a6,0xaed2ae25,0x333db363,
  0xb3652edd,0x2e1ab33a,0xb1aa227a,0x31a6b3fd,0xaf853387,0xb3102d6a,0xb22d33fe,0xb116a216,0x32a9abd3,0xb06f33c2,0x307428a6,0xb2a533ea,
  0x3111b3e9,0x3231a8be,0x330db3c3,0x2f902bba,0xb2e12e31,0x3015b360,0x288db1a1,0x33ebb1af,0xb1e733f5,0xb1662691,0xb33f2f9b,0x2ec6b30a,
  0x2ee82a19,0xb33733da,0xb15833d7,0xb1f42a63,0x33e8b313,0x28d72f7a,0x302525fb,0xb2d833f7,0xb2392d81,0x3107b383,0x3307b3fe,0x2fa6214d,
  0xb35e33ec,0xae3ca874,0x97dbb00f,0x3400b2e5,0xa5c930b7,0xb3f83276,0xb316302a,0x2f6fb2d5,0x32b0aef4,0xb0653335,0xb29e33fd,0xb07f2343,
  0xb1702ccf,0x31dfb3a1,0x3345b124,0xaeaf3221,0xb3fc336c,0xa3a7adf7,0x3332b400,0x2eff997f,0xb0b23304,0xb27a2fb2,0x2b71b102,0x33c8b23d,
  0x2c0e29e8,0xb3bd33dd,0xb0d62a94,0x3260b3d4,0xb0892c1a,0x3297b3bc,0x2aad2842,0xb3d333ee,0xb3b0327e,0x2c6fb0ad,0x3241b035,0xb0fd32ce,
  0xb35933fc,0xae542406,0x3400b392,0x1b112d2f,0xaf5931da,0xb31b3174,0x321db37f,0x3129ad99,0xaf152ac6,0x332cb3d2,0xb1463293,0xb204308e,
  0xb281312e,0x30a8b219,0xab402f4e,0xb3cb331e,0xb3ef3371,0x2829addf,0x2c269c52,0xb3ba3400,0xb37c33f2,0xada52759,0x3179afc8,0xb1d632fe,
  0xacf32953,0x339cb3e3,0xb3fa33cc,0x2500ab28,0xb0942f21,0x3290b32a,0xb3d033fb,0xaade246a,0xb249317d,0x30f3b1d2,0xb2fb337a,0xafd22db1,
  0xb37332f1,0x2dd4aff3,0xb18b3254,0xb1c530e5,0xa96c27bd,0x33e2b3f1,0xb0452fdd,0x32c4b2f7,0xac3e2af7,0x33b7b3cf,0xb0ea3099,0x3250b28c,
  0xadbc2cff,0x3378b39a,0xb1823137,0x31cdb211,0xaf2c2e76,0x3327b352,0xb20d31c9,0x313cb186,0x313c3186,0xb20db1c9,0x2d0b2dc8,0xb398b376,
  0x309e30ee,0xb289b24d,0x2b0f2c4b,0xb3ceb3b5,0x2fe8304a,0xb2f4b2c1,0x27ef2985,0xb3f0b3e1,0x2e822f37,0xb34fb324,0x1ead24ce,0xb3ffb3fa,
  0xb2bdb209,0xb050b141,0xb290b32a,0x30942f21,0xb3b3b34c,0xac57ae8d,0xb0f3b1d2,0x3249317d,0xb400b3ef,0x1d1ba810,0xadd4aff3,0x337332f1,
  0xb39cb3e3,0x2cf32953,0xa500ab28,0x33fa33cc,0xae99b0f8,0x334a3245,0x33ff33b2,0x201f2c63,0x2438a9b6,0x33fc33df,0x332c33d2,0xaf15aac6,
  0x303a2ce7,0x32cb339e,0x30a83219,0xb281b12e,0x32ee31c0,0x2ffe3190,0x28292ddf,0xb3efb371,0x33b0327e,0x2c6f30ad,0xb241b035,0xb0fdb2ce,
  0x335933fc,0xae54a406,0xb400b392,0x1b11ad2f,0x2f5931da,0xb31bb174,0xb21db37f,0x31292d99,0xaaad2842,0xb3d3b3ee,0xa9cfb005,0x33de32eb,
  0x285b305f,0xb3edb2b3,0x2c0ea9e8,0x33bd33dd,0xb170accf,0xb1dfb3a1,0x33453124,0x2eaf3221,0xb3fcb36c,0x23a7adf7,0x33323400,0xaeff997f,
  0xb0b2b304,0x327a2fb2,0x2b713102,0xb3c8b23d,0xb400b2e5,0x17dbb00f,0x2e023264,0xb36ab0d1,0xaf6fb2d5,0x3316302a,0xb11fa8f0,0xb225b3e7,
  0x307f2343,0x329e33fd,0xb3d6b38e,0x2a7cad46,0x33f53342,0xa6c32ebb,0xac87b1e3,0x33ac316b,0x28d7af7a,0x33e83313,0xb2d8b3f7,0x3025a5fb,
  0x33eb31af,0x288d31a1,0x2bebae0e,0x33c03368,0x2ec6330a,0xb33faf9b,0x33fe3235,0x21b1310c,0xb1f4aa63,0xb158b3d7,0x2d5232a2,0xb38bb07a,
  0x33a7333d,0xacab2ed2,0x33f63162,0x262d31eb,0xaa4b301a,0xb3d8b2de,0x2a32326b,0xb3d9b0c7,0xb3f6b26f,0x265fb0c1,0xb3a9b020,0xac9fb2db,
  0x0e48b15d,0x340031f0,0xae1ab33a,0x33652edd,0xaed22e25,0xb33db363,0xb1eb0e48,0xb162b400,0xb2deb3a7,0x301aacab,0xb0c7b3f6,0x326b262d,
  0x30c1aa4b,0x326f33d8,0x32db2a32,0x302033d9,0x31f033f6,0xb15d265f,0x2edd33a9,0xb33aac9f,0xb2acb385,0x306aad76,0x2a19b166,0x33da31e7,
  0x3229a2de,0x311b33fd,0x33133337,0xaf7a2ee8,0x2e3133c5,0xb360aba2,0xb1a128d7,0xb1afb3e8,0xb3f5b015,0xa691b2e1,0xaf9bb3eb,0x330a288d,
  0x3154acc3,0x31f833a3,0x2ef433f8,0xb335a5c9,0x2d8133dc,0xb383aa01,0xb3feb065,0x214db2b0,0xb3ecb107,0x2874b239,0x300fafa6,0x32e53307,
  0x30b7ae3c,0x3276335e,0x302a3400,0xb2d517db,0x312433bd,0xb2212c0e,0xb318b260,0x2f64b0d6,0xb400aeaf,0x997fb345,0x335c20e8,0x2e4833fe,
  0x3102aeff,0x323d3332,0xac7b31fc,0xb3aeb14f,0x2a9433c8,0xb3d4ab71,0xb084b3e6,0x329ba909,0xb2ce2aad,0xb035b3d3,0x33e529cf,0x292233de,
  0x2d2fb241,0x339230fd,0xb14a2fbd,0xb200b301,0x2d993400,0xb37f1b11,0x2084b36f,0x33ff2deb,0xb2ebb21d,0x3005b129,0x30db339f,0xb25c2cdb,
  0xae5fb3e4,0x3357a93b,0xb190303a,0xb1c0b2cb,0x32453258,0xb0f830e0,0x2c63b2ee,0x33b22ffe,0xb3dfae99,0x29b6b34a,0x2ac633ff,0xb3d2a01f,
  0x339ea438,0x2ce733fc,0xb12eb32c,0x3219af15,0x33b8a78b,0x2c3233f2,0x2810b3b3,0x33ef2c57,0xb2c72e6b,0xb040b354,0x29533400,0xb3e31d1b,
  0x3141b133,0x32093215,0xaf21b39c,0x332aacf3,0xae8d32bd,0xb34cb050,0x317d3290,0xb1d23094,0x27bd33fb,0xb3f1249c,0x2fdd3327,0xb2f72f2c,
  0xaaf7b3e2,0x33cfa96c,0xb099b2c4,0x328cb045,0x2cff33b7,0xb39a2c3e,0x31373250,0xb21130ea,0xae76b378,0x3352adbc,0xb1c9b1cd,0x3186b182,
  0xb3ff1ead,0x1de4b3ff,0xb352adbc,0x2e76b378,0x33f1249c,0xa7bd33fb,0x32f72f2c,0xafdd3327,0xb3cfa96c,0x2af7b3e2,0xb28cb045,0x3099b2c4,
  0x339a2c3e,0xacff33b7,0x321130ea,0xb1373250,0x2953b400,0x33e31d1b,0x33ccadd4,0x2b283373,0xaf21339c,0xb32aacf3,0xb3fb2500,0x246ab3fa,
  0x317db290,0x31d23094,0x337a2ade,0xadb133d0,0xb2f130f3,0xaff3b249,0xb254afd2,0x30e5b2fb,0x339e2438,0xace733fc,0xb12e332c,0xb219af15,
  0xb190b03a,0x31c0b2cb,0x3371b0a8,0x2ddf3281,0x2c6332ee,0xb3b22ffe,0xb3f22829,0x2759b3ef,0x2ac6b3ff,0x33d2a01f,0x32932da5,0xb08e337c,
  0xaf0a33f3,0xb32fa727,0x2406b3b0,0x33fcac6f,0x3347b194,0x2ea431bc,0xb1743359,0xb1daae54,0xb3bc2565,0x2c1ab3f9,0x33eeaf59,0x2842331b,
  0x30ad3089,0xb27e3297,0xb2ceaaad,0x3035b3d3,0xb29ba909,0x3084b3e6,0x305f3030,0xb2b332d1,0x259732e8,0xb3f8300a,0x2ccfb3ed,0x33a1a85b,
  0x31b8b381,0x31992d8d,0xb36c31df,0xadf7b170,0xb3f42d3a,0x26f5b390,0x330423a7,0xafb233fc,0x316bb3d6,0x31e32a7c,0xb3832a01,0x2d81b3dc,
  0xb3bf2c87,0x2c02b3ac,0x28743239,0xb3ec3107,0x2b8931b3,0xb3c6319d,0x3276b35e,0x30b72e3c,0x31f8b3a3,0x31542cc3,0xb33525c9,0x2ef4b3f8,
  0x310c2beb,0xb23533c0,0x33abb267,0x2c9330cc,0x307ab3fe,0x32a2a1b1,0xb06aad76,0x32acb385,0xb3a52d52,0x2cb7b38b,0xb11b33fd,0xb229a2de,
  0x94b63273,0xb40030bc,0x3360aba2,0xae3133c5,0xb2de33a7,0xb01aacab,0xb0c733f6,0xb26b262d,0x30c12a4b,0xb26f33d8,0x32dbaa32,0xb02033d9,
  0x31f0b3f6,0x315d265f,0x2eddb3a9,0x333aac9f,0xb1eb8e48,0x3162b400,0xb3872e1a,0x2d6ab365,0xae25ad5e,0x3363b389,0x8e48b15d,0x3400b1f0,
  0xb3a7333d,0xacabaed2,0xb3f63162,0x262db1eb,0x2a4b301a,0xb3d832de,0xaa32326b,0xb3d930c7,0x33f6b26f,0x265f30c1,0x33a9b020,0xac9f32db,
  0x33c0b368,0x2beb2e0e,0x30cc94b6,0xb2673400,0x21b1b10c,0x33feb235,0x3385b3ab,0x2d762c93,0xb38b307a,0x2d52b2a2,0xa2deb06a,0x33fdb2ac,
  0xb0bc33a5,0xb2732cb7,0xb3c5311b,0x2ba2b229,0x26c32ebb,0xb3f53342,0xb3ac316b,0x2c87b1e3,0x336ab0d1,0xae023264,0xb19d33bf,0xb1b32c02,
  0x3225b3e7,0x311fa8f0,0x2cc32b89,0xb3a333c6,0xaa7cad46,0x33d6b38e,0x33dcb1f8,0xaa013154,0xb3fe3318,0x20e8af64,0x3381b3f8,0x2d8d2597,
  0xb14f335c,0xb1fc2e48,0x2d3ab199,0x3390b1b8,0x29092c7b,0xb3e633ae,0xb03026f5,0x32d1b3f4,0x32e8b084,0xb00a329b,0xb3ed32b3,0x285bb05f,
  0x29cfb005,0x33deb2eb,0xb05a325c,0xb2b630db,0xafbd2922,0x3301b3e5,0x27272b59,0xb3f333c9,0xb36f3200,0x2debb14a,0x31bcaf0a,0xb194332f,
  0xb39f33ff,0xacdba084,0x33f9b347,0xa5652ea4,0x3394b2ba,0xad233055,0xa438a9b6,0x33fcb3df,0x33e4b3f9,0x293b2533,0xb03a2ce7,0x32cbb39e,
  0x3258b357,0x30e0ae5f,0xb2ee31c0,0x2ffeb190,0x2e99b0f8,0x334ab245,0xb3ff33b2,0x201fac63,0xaf4230a3,0xb3213285,0x3133b040,0xb21532c7,
  0xa99e2d17,0xb3e03396,0x32bdb209,0xb0503141,0x278b1f76,0xb3f233ff,0x33b3b34c,0xac572e8d,0x2e6bac32,0xb35433b8,0x3400b3ef,0x1d1b2810,
  0xb289324d,0x309eb0ee,0xb3ce33b5,0x2b0fac4b,0xb2f432c1,0x2fe8b04a,0xb3f033e1,0x27efa985,0xb34f3324,0x2e82af37,0xb3ff33fa,0x1eada4ce,
  0xb3983376,0x2d0badc8,0xb3fb33ff,0xa49c1de4,0x351c35f6,0xac93a617,0xb8a3b93c,0x308d2a16,0x32f43448,0xb160afa5,0xb6a4b7fe,0x353a3389,
  0x2fa53160,0xb448b2f4,0xb389b53a,0x37fe36a4,0x26172c93,0xb5f6b51c,0xaa16b08d,0x393c38a3,0x34c3358c,0xac47a5b2,0xb85fb8f3,0x304229b1,
  0x327e33fd,0xb106af26,0xb63cb785,0x34e7330f,0x2f263106,0xb3fdb27e,0xb30fb4e7,0x3785363c,0x25b22c47,0xb58cb4c3,0xa9b1b042,0x38f3385f,
  0x346a3523,0xabf6a54d,0xb81ab8a8,0x2fef294d,0x3209336b,0xb0acaea7,0xb5d4b70a,0x34933294,0x2ea730ac,0xb36bb209,0xb294b493,0x370a35d4,
  0x254d2bf6,0xb523b46a,0xa94dafef,0x38a8381a,0x341334bc,0xab5fa4e9,0xb7a6b85a,0x2f5928e8,0x319432da,0xb052ae28,0xb56ab68d,0x343e3219,
  0x2e283052,0xb2dab194,0xb219b43e,0x368d356a,0x24e92b5f,0xb4bcb413,0xa8e8af59,0x385a37a6,0x33783456,0xaac8a484,0xb715b80a,0x2ec32884,
  0x3120324a,0xaff2ada9,0xb4ffb60e,0x33d3319e,0x2da92ff2,0xb24ab120,0xb19eb3d3,0x360e34ff,0x24842ac8,0xb456b378,0xa884aec3,0x380a3715,
  0x32cd33e3,0xaa31a420,0xb682b76f,0x2e2d281f,0x30ac31bb,0xaf3fad2a,0xb493b58d,0x33283122,0x2d2a2f3f,0xb1bbb0ac,0xb122b328,0x358d3493,
  0x24202a31,0xb3e3b2cd,0xa81fae2d,0x376f3682,0x3223331c,0xa999a376,0xb5ebb6c6,0x2d972776,0x3039312d,0xae8dacac,0xb426b50b,0x327c30a6,
  0x2cac2e8d,0xb12db039,0xb0a6b27c,0x350b3426,0x23762999,0xb31cb223,0xa776ad97,0x36c635eb,0x317a3257,0xa902a2ad,0xb552b61a,0x2d0026ad,
  0x2f8c309f,0xaddcac2e,0xb371b487,0x31cf3029,0x2c2e2ddc,0xb09faf8c,0xb029b1cf,0x34873371,0x22ad2902,0xb257b17a,0xa6adad00,0x361a3552,
  0x30d23194,0xa86ba1e4,0xb4b7b56a,0x2c6a25e4,0x2ea73012,0xad2aab5f,0xb294b402,0x31222f59,0x2b5f2d2a,0xb012aea7,0xaf59b122,0x34023294,
  0x21e4286b,0xb194b0d2,0xa5e4ac6a,0x356a34b7,0x302c30d2,0xa7a9a11b,0xb41ab4b7,0x2ba7251b,0x2dc22f0c,0xac79aa63,0xb1b6b2f7,0x30742e5f,
  0x2a632c79,0xaf0cadc2,0xae5fb074,0x32f731b6,0x211b27a9,0xb0d2b02c,0xa51baba7,0x34b7341a,0x2f0c3012,0xa67ba052,0xb2f7b402,0x2a7a2452,
  0x2cde2df5,0xab91a967,0xb0d7b1e8,0x2f8b2d65,0x29672b91,0xadf5acde,0xad65af8b,0x31e830d7,0x2052267b,0xb012af0c,0xa452aa7a,0x340232f7,
  0x2dc22ea7,0xa54d9f12,0xb1b6b294,0x294d2311,0x2bf62cde,0xaa31a86b,0xafefb0d7,0x2e2d2c6a,0x286b2a31,0xacdeabf6,0xac6aae2d,0x30d72fef,
  0x1f12254d,0xaea7adc2,0xa311a94d,0x329431b6,0x2c792d2a,0xa4209d7f,0xb074b122,0x281f217f,0x2a312b91,0xa8d0a6e0,0xae2daf8b,0x2cce2ade,
  0x26e028d0,0xab91aa31,0xaadeacce,0x2f8b2e2d,0x1d7f2420,0xad2aac79,0xa17fa81f,0x31223074,0x2a632b5f,0xa1e49bdb,0xae5faf59,0x25e41fdb,
  0x286b2967,0xa6e0a4e9,0xac6aad65,0x2ade28e8,0x24e926e0,0xa967a86b,0xa8e8aade,0x2d652c6a,0x1bdb21e4,0xab5faa63,0x9fdba5e4,0x2f592e5f,
  0x27a9286b,0x9f1298b6,0xaba7ac6a,0x23111cb6,0x254d267b,0xa420a1e4,0xa94daa7a,0x281f25e4,0x21e42420,0xa67ba54d,0xa5e4a81f,0x2a7a294d,
  0x18b61f12,0xa86ba7a9,0x9cb6a311,0x2c6a2ba7,0x211b21e4,0x98b69248,0xa51ba5e4,0x1cb61648,0x1f122052,0x9d7f9bdb,0xa311a452,0x217f1fdb,
  0x1bdb1d7f,0xa0529f12,0x9fdba17f,0x24522311,0x124818b6,0xa1e4a11b,0x96489cb6,0x25e4251b,0xa11ba1e4,0x18b61248,0x251b25e4,0x9cb69648,
  0x9f12a052,0x1d7f1bdb,0x23112452,0xa17f9fdb,0x9bdb9d7f,0x20521f12,0x1fdb217f,0xa452a311,0x924898b6,0x21e4211b,0x16481cb6,0xa5e4a51b,
  0xa7a9a86b,0x1f1218b6,0x2ba72c6a,0xa3119cb6,0xa54da67b,0x242021e4,0x294d2a7a,0xa81fa5e4,0xa1e4a420,0x267b254d,0x25e4281f,0xaa7aa94d,
  0x98b69f12,0x286b27a9,0x1cb62311,0xac6aaba7,0xaa63ab5f,0x21e41bdb,0x2e5f2f59,0xa5e49fdb,0xa86ba967,0x26e024e9,0x2c6a2d65,0xaadea8e8,
  0xa4e9a6e0,0x2967286b,0x28e82ade,0xad65ac6a,0x9bdba1e4,0x2b5f2a63,0x1fdb25e4,0xaf59ae5f,0xac79ad2a,0x24201d7f,0x30743122,0xa81fa17f,
  0xaa31ab91,0x28d026e0,0x2e2d2f8b,0xacceaade,0xa6e0a8d0,0x2b912a31,0x2ade2cce,0xaf8bae2d,0x9d7fa420,0x2d2a2c79,0x217f281f,0xb122b074,
  0xadc2aea7,0x254d1f12,0x31b63294,0xa94da311,0xabf6acde,0x2a31286b,0x2fef30d7,0xae2dac6a,0xa86baa31,0x2cde2bf6,0x2c6a2e2d,0xb0d7afef,
  0x9f12a54d,0x2ea72dc2,0x2311294d,0xb294b1b6,0xaf0cb012,0x267b2052,0x32f73402,0xaa7aa452,0xacdeadf5,0x2b912967,0x30d731e8,0xaf8bad65,
  0xa967ab91,0x2df52cde,0x2d652f8b,0xb1e8b0d7,0xa052a67b,0x30122f0c,0x24522a7a,0xb402b2f7,0xb02cb0d2,0x27a9211b,0x341a34b7,0xaba7a51b,
  0xadc2af0c,0x2c792a63,0x31b632f7,0xb074ae5f,0xaa63ac79,0x2f0c2dc2,0x2e5f3074,0xb2f7b1b6,0xa11ba7a9,0x30d2302c,0x251b2ba7,0xb4b7b41a,
  0xb0d2b194,0x286b21e4,0x34b7356a,0xac6aa5e4,0xaea7b012,0x2d2a2b5f,0x32943402,0xb122af59,0xab5fad2a,0x30122ea7,0x2f593122,0xb402b294,
  0xa1e4a86b,0x319430d2,0x25e42c6a,0xb56ab4b7,0xb17ab257,0x290222ad,0x3552361a,0xad00a6ad,0xaf8cb09f,0x2ddc2c2e,0x33713487,0xb1cfb029,
  0xac2eaddc,0x309f2f8c,0x302931cf,0xb487b371,0xa2ada902,0x3257317a,0x26ad2d00,0xb61ab552,0xb223b31c,0x29992376,0x35eb36c6,0xad97a776,
  0xb039b12d,0x2e8d2cac,0x3426350b,0xb27cb0a6,0xacacae8d,0x312d3039,0x30a6327c,0xb50bb426,0xa376a999,0x331c3223,0x27762d97,0xb6c6b5eb,
  0xb2cdb3e3,0x2a312420,0x3682376f,0xae2da81f,0xb0acb1bb,0x2f3f2d2a,0x3493358d,0xb328b122,0xad2aaf3f,0x31bb30ac,0x31223328,0xb58db493,
  0xa420aa31,0x33e332cd,0x281f2e2d,0xb76fb682,0xb378b456,0x2ac82484,0x3715380a,0xaec3a884,0xb120b24a,0x2ff22da9,0x34ff360e,0xb3d3b19e,
  0xada9aff2,0x324a3120,0x319e33d3,0xb60eb4ff,0xa484aac8,0x34563378,0x28842ec3,0xb80ab715,0xb413b4bc,0x2b5f24e9,0x37a6385a,0xaf59a8e8,
  0xb194b2da,0x30522e28,0x356a368d,0xb43eb219,0xae28b052,0x32da3194,0x3219343e,0xb68db56a,0xa4e9ab5f,0x34bc3413,0x28e82f59,0xb85ab7a6,
  0xb46ab523,0x2bf6254d,0x381a38a8,0xafefa94d,0xb209b36b,0x30ac2ea7,0x35d4370a,0xb493b294,0xaea7b0ac,0x336b3209,0x32943493,0xb70ab5d4,
  0xa54dabf6,0x3523346a,0x294d2fef,0xb8a8b81a,0xb4c3b58c,0x2c4725b2,0x385f38f3,0xb042a9b1,0xb27eb3fd,0x31062f26,0x363c3785,0xb4e7b30f,
  0xaf26b106,0x33fd327e,0x330f34e7,0xb785b63c,0xa5b2ac47,0x358c34c3,0x29b13042,0xb8f3b85f,0xb51cb5f6,0x2c932617,0x38a3393c,0xb08daa16,
  0xb2f4b448,0x31602fa5,0x36a437fe,0xb53ab389,0xafa5b160,0x344832f4,0x3389353a,0xb7feb6a4,0xa617ac93,0x35f6351c,0x2a16308d,0xb93cb8a3,
};
__device__ __align__(128) const uint32_t c_img[2560] = {
  0x326d31ed,0x333b32dd,0x33c33388,0x33fe33ea,0x33c331ed,0x31ed33c3,0xa8b22d64,0xb33bb0c4,0x33ea31ed,0xad64301d,0xb2ddb388,0x315fa8b2,
  0x32dd31ed,0xb3feabc6,0x326dad64,0xad64326d,0x30c431ed,0xaed7b2dd,0x2bc63388,0xa248b3ea,0x2bc631ed,0x315fb3c3,0xb3ea2d64,0x2ed730c4,
  0xa8b231ed,0x3388b01d,0x301db388,0xb1ed28b2,0xb01d31ed,0x22482bc6,0x30c4ad64,0x3388b26d,0x33ea33fe,0x338833c3,0x32dd333b,0x31ed326d,
  0xb2ddb3fe,0xa248b01d,0x326d2ed7,0x338833ea,0x30c433fe,0xb33babc6,0xabc6b33b,0x33fe30c4,0xabc6b3fe,0x31ed32dd,0xb3eaaed7,0x333ba8b2,
  0xa8b233fe,0x2d64b3c3,0xb01d333b,0x315fb26d,0x301db3fe,0xb3fe301d,0x30c42ed7,0x2d64b3ea,0xb26d33fe,0x2ed72bc6,0x33c3b33b,0xa248b0c4,
  0x33c3b3fe,0x315fb2dd,0x28b2aed7,0xaed728b2,0xb0c4b15f,0xaed7b01d,0xabc6ad64,0xa248a8b2,0xabc6b15f,0x315f2bc6,0x33ea3388,0x2ed7326d,
  0x28b2b15f,0x338832dd,0xb01d2d64,0xb1edb3ea,0x301db15f,0x224833c3,0xb0c4b388,0x338830c4,0x326db15f,0xb33b301d,0x33c3ad64,0xb3fe28b2,
  0x33c3b15f,0xb1edabc6,0xa8b23388,0x333bb26d,0x33eab15f,0x2d64b2dd,0xb2dd2d64,0xb15f33ea,0x32ddb15f,0x33feb3c3,0x326db388,0x2d64b0c4,
  0x28b22248,0x2d642bc6,0x301d2ed7,0x315f30c4,0xb01da248,0xb3feb2dd,0xb0c4b33b,0x2d64a8b2,0x326d2248,0x2ed733c3,0xb3c3aed7,0xa248b26d,
  0xb3c3a248,0x315fb01d,0xa8b2333b,0xaed7b3ea,0x33ea2248,0xb388abc6,0x32dd2ed7,0xb1edb0c4,0xb2dda248,0x224832dd,0x326db33b,0xb38828b2,
  0x30c42248,0x333bb3c3,0xabc6aed7,0xb3fe326d,0xabc6a248,0xb1ed301d,0xb3ea333b,0xb33b33ea,0xb26d31ed,0xb33b32dd,0xb3c33388,0xb3fe33ea,
  0xb3c331ed,0xb1ed33c3,0x28b22d64,0x333bb0c4,0xb3ea31ed,0x2d64301d,0x32ddb388,0xb15fa8b2,0xb2dd31ed,0x33feabc6,0xb26dad64,0x2d64326d,
  0xb0c431ed,0x2ed7b2dd,0xabc63388,0x2248b3ea,0xabc631ed,0xb15fb3c3,0x33ea2d64,0xaed730c4,0x28b231ed,0xb388b01d,0xb01db388,0x31ed28b2,
  0x301d31ed,0xa2482bc6,0xb0c4ad64,0xb388b26d,0xb3ea33fe,0xb38833c3,0xb2dd333b,0xb1ed326d,0x32ddb3fe,0x2248b01d,0xb26d2ed7,0xb38833ea,
  0xb0c433fe,0x333babc6,0x2bc6b33b,0xb3fe30c4,0x2bc6b3fe,0xb1ed32dd,0x33eaaed7,0xb33ba8b2,0x28b233fe,0xad64b3c3,0x301d333b,0xb15fb26d,
  0xb01db3fe,0x33fe301d,0xb0c42ed7,0xad64b3ea,0x326d33fe,0xaed72bc6,0xb3c3b33b,0x2248b0c4,0xb3c3b3fe,0xb15fb2dd,0xa8b2aed7,0x2ed728b2,
  0x30c4b15f,0x2ed7b01d,0x2bc6ad64,0x2248a8b2,0x2bc6b15f,0xb15f2bc6,0xb3ea3388,0xaed7326d,0xa8b2b15f,0xb38832dd,0x301d2d64,0x31edb3ea,
  0xb01db15f,0xa24833c3,0x30c4b388,0xb38830c4,0xb26db15f,0x333b301d,0xb3c3ad64,0x33fe28b2,0xb3c3b15f,0x31edabc6,0x28b23388,0xb33bb26d,
  0xb3eab15f,0xad64b2dd,0x32dd2d64,0x315f33ea,0xb2ddb15f,0xb3feb3c3,0xb26db388,0xad64b0c4,0xa8b22248,0xad642bc6,0xb01d2ed7,0xb15f30c4,
  0x301da248,0x33feb2dd,0x30c4b33b,0xad64a8b2,0xb26d2248,0xaed733c3,0x33c3aed7,0x2248b26d,0x33c3a248,0xb15fb01d,0x28b2333b,0x2ed7b3ea,
  0xb3ea2248,0x3388abc6,0xb2dd2ed7,0x31edb0c4,0x32dda248,0xa24832dd,0xb26db33b,0x338828b2,0xb0c42248,0xb33bb3c3,0x2bc6aed7,0x33fe326d,
  0x2bc6a248,0x31ed301d,0x33ea333b,0x333b33ea,0x30c4315f,0x2ed7301d,0x2bc62d64,0x224828b2,0x2bc6315f,0xb15fabc6,0xb3eab388,0xaed7b26d,
  0xa8b2315f,0xb388b2dd,0x301dad64,0x31ed33ea,0xb01d315f,0xa248b3c3,0x30c43388,0xb388b0c4,0xb26d315f,0x333bb01d,0xb3c32d64,0x33fea8b2,
  0xb3c3315f,0x31ed2bc6,0x28b2b388,0xb33b326d,0xb3ea315f,0xad6432dd,0x32ddad64,0x315fb3ea,0xb2dd315f,0xb3fe33c3,0xb26d3388,0xad6430c4,
  0xa8b2a248,0xad64abc6,0xb01daed7,0xb15fb0c4,0x301d2248,0x33fe32dd,0x30c4333b,0xad6428b2,0xb26da248,0xaed7b3c3,0x33c32ed7,0x2248326d,
  0x33c32248,0xb15f301d,0x28b2b33b,0x2ed733ea,0xb3eaa248,0x33882bc6,0xb2ddaed7,0x31ed30c4,0x32dd2248,0xa248b2dd,0xb26d333b,0x3388a8b2,
  0xb0c4a248,0xb33b33c3,0x2bc62ed7,0x33feb26d,0x2bc62248,0x31edb01d,0x33eab33b,0x333bb3ea,0x326d31ed,0x333b32dd,0x33c33388,0x33fe33ea,
  0x33c331ed,0x31ed33c3,0xa8b22d64,0xb33bb0c4,0x33ea31ed,0xad64301d,0xb2ddb388,0x315fa8b2,0x32dd31ed,0xb3feabc6,0x326dad64,0xad64326d,
  0x30c431ed,0xaed7b2dd,0x2bc63388,0xa248b3ea,0x2bc631ed,0x315fb3c3,0xb3ea2d64,0x2ed730c4,0xa8b231ed,0x3388b01d,0x301db388,0xb1ed28b2,
  0xb01d31ed,0x22482bc6,0x30c4ad64,0x3388b26d,0x33ea33fe,0x338833c3,0x32dd333b,0x31ed326d,0xb2ddb3fe,0xa248b01d,0x326d2ed7,0x338833ea,
  0x30c433fe,0xb33babc6,0xabc6b33b,0x33fe30c4,0xabc6b3fe,0x31ed32dd,0xb3eaaed7,0x333ba8b2,0xa8b233fe,0x2d64b3c3,0xb01d333b,0x315fb26d,
  0x301db3fe,0xb3fe301d,0x30c42ed7,0x2d64b3ea,0xb26d33fe,0x2ed72bc6,0x33c3b33b,0xa248b0c4,0x33c3b3fe,0x315fb2dd,0x28b2aed7,0xaed728b2,
  0xb0c4315f,0xaed7301d,0xabc62d64,0xa24828b2,0xabc6315f,0x315fabc6,0x33eab388,0x2ed7b26d,0x28b2315f,0x3388b2dd,0xb01dad64,0xb1ed33ea,
  0x301d315f,0x2248b3c3,0xb0c43388,0x3388b0c4,0x326d315f,0xb33bb01d,0x33c32d64,0xb3fea8b2,0x33c3315f,0xb1ed2bc6,0xa8b2b388,0x333b326d,
  0x33ea315f,0x2d6432dd,0xb2ddad64,0xb15fb3ea,0x32dd315f,0x33fe33c3,0x326d3388,0x2d6430c4,0x28b2a248,0x2d64abc6,0x301daed7,0x315fb0c4,
  0xb01d2248,0xb3fe32dd,0xb0c4333b,0x2d6428b2,0x326da248,0x2ed7b3c3,0xb3c32ed7,0xa248326d,0xb3c32248,0x315f301d,0xa8b2b33b,0xaed733ea,
  0x33eaa248,0xb3882bc6,0x32ddaed7,0xb1ed30c4,0xb2dd2248,0x2248b2dd,0x326d333b,0xb388a8b2,0x30c4a248,0x333b33c3,0xabc62ed7,0xb3feb26d,
  0xabc62248,0xb1edb01d,0xb3eab33b,0xb33bb3ea,0xb26d31ed,0xb33b32dd,0xb3c33388,0xb3fe33ea,0xb3c331ed,0xb1ed33c3,0x28b22d64,0x333bb0c4,
  0xb3ea31ed,0x2d64301d,0x32ddb388,0xb15fa8b2,0xb2dd31ed,0x33feabc6,0xb26dad64,0x2d64326d,0xb0c431ed,0x2ed7b2dd,0xabc63388,0x2248b3ea,
  0xabc631ed,0xb15fb3c3,0x33ea2d64,0xaed730c4,0x28b231ed,0xb388b01d,0xb01db388,0x31ed28b2,0x301d31ed,0xa2482bc6,0xb0c4ad64,0xb388b26d,
  0xb3ea33fe,0xb38833c3,0xb2dd333b,0xb1ed326d,0x32ddb3fe,0x2248b01d,0xb26d2ed7,0xb38833ea,0xb0c433fe,0x333babc6,0x2bc6b33b,0xb3fe30c4,
  0x2bc6b3fe,0xb1ed32dd,0x33eaaed7,0xb33ba8b2,0x28b233fe,0xad64b3c3,0x301d333b,0xb15fb26d,0xb01db3fe,0x33fe301d,0xb0c42ed7,0xad64b3ea,
  0x326d33fe,0xaed72bc6,0xb3c3b33b,0x2248b0c4,0xb3c3b3fe,0xb15fb2dd,0xa8b2aed7,0x2ed728b2,0x29ed29ed,0x29ed29ed,0x29ed29ed,0x29ed29ed,
  0x2bc32a6d,0x2add2bea,0x23c628c4,0xa81da0b2,0x2bc32add,0xa3c6281d,0xabc3aadd,0x23c6a81d,0x29ed2b3b,0xabfea564,0x295fa6d7,0x1a482b88,
  0x25642b88,0xa564ab88,0x25642b88,0xa564ab88,0xa0b22bc3,0x2a6daadd,0xabea23c6,0x28c4281d,0xa8c42bea,0x2a6da0b2,0x28c4abea,0xaa6d20b2,
  0xab3b2bfe,0xa564295f,0x26d79a48,0x2b88a9ed,0x29ed29ed,0x29ed29ed,0x29ed29ed,0x29ed29ed,0xabc3aa6d,0xaaddabea,0xa3c6a8c4,0x281d20b2,
  0x2bc32add,0xa3c6281d,0xabc3aadd,0x23c6a81d,0xa9edab3b,0x2bfe2564,0xa95f26d7,0x9a48ab88,0x25642b88,0xa564ab88,0x25642b88,0xa564ab88,
  0x20b2abc3,0xaa6d2add,0x2beaa3c6,0xa8c4a81d,0xa8c42bea,0x2a6da0b2,0x28c4abea,0xaa6d20b2,0x2b3babfe,0x2564a95f,0xa6d71a48,0xab8829ed,
  0x295f295f,0x295f295f,0x295f295f,0x295f295f,0x23c628c4,0xa81da0b2,0xabc3aa6d,0xaaddabea,0xa3c6281d,0xabc3aadd,0x23c6a81d,0x2bc32add,
  0xa95f26d7,0x9a48ab88,0x29ed2b3b,0xabfea564,0xab882564,0x2b88a564,0xab882564,0x2b88a564,0xabea23c6,0x28c4281d,0x20b2abc3,0xaa6d2add,
  0xaa6d20b2,0xa8c42bea,0x2a6da0b2,0x28c4abea,0xa6d71a48,0xab8829ed,0xab3b2bfe,0xa564295f,0x295f295f,0x295f295f,0x295f295f,0x295f295f,
  0xa3c6a8c4,0x281d20b2,0x2bc32a6d,0x2add2bea,0xa3c6281d,0xabc3aadd,0x23c6a81d,0x2bc32add,0x295fa6d7,0x1a482b88,0xa9edab3b,0x2bfe2564,
  0xab882564,0x2b88a564,0xab882564,0x2b88a564,0x2beaa3c6,0xa8c4a81d,0xa0b22bc3,0x2a6daadd,0xaa6d20b2,0xa8c42bea,0x2a6da0b2,0x28c4abea,
  0x26d79a48,0x2b88a9ed,0x2b3babfe,0x2564a95f,0xabfe2bfe,0xabfe2bfe,0xabfe2bfe,0xabfe2bfe,0xaadd2bea,0xa3c628c4,0x281da0b2,0x2bc3aa6d,
  0xa81d2bc3,0x2adda3c6,0x281dabc3,0xaadd23c6,0x9a482b88,0x29edab3b,0xabfe2564,0x295f26d7,0x26d72b3b,0xa6d7ab3b,0x26d72b3b,0xa6d7ab3b,
  0x2a6d2add,0xabeaa3c6,0x28c4a81d,0x20b22bc3,0x2bea2a6d,0xa0b228c4,0xabeaaa6d,0x20b2a8c4,0x2b8829ed,0x2b3b2bfe,0x2564295f,0xa6d79a48,
  0xabfe2bfe,0xabfe2bfe,0xabfe2bfe,0xabfe2bfe,0x2addabea,0x23c6a8c4,0xa81d20b2,0xabc32a6d,0xa81d2bc3,0x2adda3c6,0x281dabc3,0xaadd23c6,
  0x1a48ab88,0xa9ed2b3b,0x2bfea564,0xa95fa6d7,0x26d72b3b,0xa6d7ab3b,0x26d72b3b,0xa6d7ab3b,0xaa6daadd,0x2bea23c6,0xa8c4281d,0xa0b2abc3,
  0x2bea2a6d,0xa0b228c4,0xabeaaa6d,0x20b2a8c4,0xab88a9ed,0xab3babfe,0xa564a95f,0x26d71a48,0x1a489a48,0x1a489a48,0x1a489a48,0x1a489a48,
  0x281da0b2,0x2bc3aa6d,0x2addabea,0x23c6a8c4,0x2adda3c6,0x281dabc3,0xaadd23c6,0xa81d2bc3,0x2bfea564,0xa95fa6d7,0x9a482b88,0x29edab3b,
  0x2b3ba6d7,0xab3b26d7,0x2b3ba6d7,0xab3b26d7,0x28c4a81d,0x20b22bc3,0xaa6daadd,0x2bea23c6,0x20b2a8c4,0x2bea2a6d,0xa0b228c4,0xabeaaa6d,
  0xa564a95f,0x26d71a48,0x2b8829ed,0x2b3b2bfe,0x1a489a48,0x1a489a48,0x1a489a48,0x1a489a48,0xa81d20b2,0xabc32a6d,0xaadd2bea,0xa3c628c4,
  0x2adda3c6,0x281dabc3,0xaadd23c6,0xa81d2bc3,0xabfe2564,0x295f26d7,0x1a48ab88,0xa9ed2b3b,0x2b3ba6d7,0xab3b26d7,0x2b3ba6d7,0xab3b26d7,
  0xa8c4281d,0xa0b2abc3,0x2a6d2add,0xabeaa3c6,0x20b2a8c4,0x2bea2a6d,0xa0b228c4,0xabeaaa6d,0x2564295f,0xa6d79a48,0xab88a9ed,0xab3babfe,
  0xa95fa95f,0xa95fa95f,0xa95fa95f,0xa95fa95f,0xa3c6a8c4,0x281d20b2,0x2bc32a6d,0x2add2bea,0x23c6a81d,0x2bc32add,0xa3c6281d,0xabc3aadd,
  0x295fa6d7,0x1a482b88,0xa9edab3b,0x2bfe2564,0x2b88a564,0xab882564,0x2b88a564,0xab882564,0x2beaa3c6,0xa8c4a81d,0xa0b22bc3,0x2a6daadd,
  0x2a6da0b2,0x28c4abea,0xaa6d20b2,0xa8c42bea,0x26d79a48,0x2b88a9ed,0x2b3babfe,0x2564a95f,0xa95fa95f,0xa95fa95f,0xa95fa95f,0xa95fa95f,
  0x23c628c4,0xa81da0b2,0xabc3aa6d,0xaaddabea,0x23c6a81d,0x2bc32add,0xa3c6281d,0xabc3aadd,0xa95f26d7,0x9a48ab88,0x29ed2b3b,0xabfea564,
  0x2b88a564,0xab882564,0x2b88a564,0xab882564,0xabea23c6,0x28c4281d,0x20b2abc3,0xaa6d2add,0x2a6da0b2,0x28c4abea,0xaa6d20b2,0xa8c42bea,
  0xa6d71a48,0xab8829ed,0xab3b2bfe,0xa564295f,0x29ed29ed,0x29ed29ed,0x29ed29ed,0x29ed29ed,0x2bc32a6d,0x2add2bea,0x23c628c4,0xa81da0b2,
  0x2bc32add,0xa3c6281d,0xabc3aadd,0x23c6a81d,0x29ed2b3b,0xabfea564,0x295fa6d7,0x1a482b88,0x25642b88,0xa564ab88,0x25642b88,0xa564ab88,
  0xa0b22bc3,0x2a6daadd,0xabea23c6,0x28c4281d,0xa8c42bea,0x2a6da0b2,0x28c4abea,0xaa6d20b2,0xab3b2bfe,0xa564295f,0x26d79a48,0x2b88a9ed,
  0x29ed29ed,0x29ed29ed,0x29ed29ed,0x29ed29ed,0xabc3aa6d,0xaaddabea,0xa3c6a8c4,0x281d20b2,0x2bc32add,0xa3c6281d,0xabc3aadd,0x23c6a81d,
  0xa9edab3b,0x2bfe2564,0xa95f26d7,0x9a48ab88,0x25642b88,0xa564ab88,0x25642b88,0xa564ab88,0x20b2abc3,0xaa6d2add,0x2beaa3c6,0xa8c4a81d,
  0xa8c42bea,0x2a6da0b2,0x28c4abea,0xaa6d20b2,0x2b3babfe,0x2564a95f,0xa6d71a48,0xab8829ed,0x9a481a48,0x9a481a48,0x9a481a48,0x9a481a48,
  0xa81d20b2,0xabc32a6d,0xaadd2bea,0xa3c628c4,0xaadd23c6,0xa81d2bc3,0x2adda3c6,0x281dabc3,0xabfe2564,0x295f26d7,0x1a48ab88,0xa9ed2b3b,
  0xab3b26d7,0x2b3ba6d7,0xab3b26d7,0x2b3ba6d7,0xa8c4281d,0xa0b2abc3,0x2a6d2add,0xabeaa3c6,0xa0b228c4,0xabeaaa6d,0x20b2a8c4,0x2bea2a6d,
  0x2564295f,0xa6d79a48,0xab88a9ed,0xab3babfe,0x9a481a48,0x9a481a48,0x9a481a48,0x9a481a48,0x281da0b2,0x2bc3aa6d,0x2addabea,0x23c6a8c4,
  0xaadd23c6,0xa81d2bc3,0x2adda3c6,0x281dabc3,0x2bfea564,0xa95fa6d7,0x9a482b88,0x29edab3b,0xab3b26d7,0x2b3ba6d7,0xab3b26d7,0x2b3ba6d7,
  0x28c4a81d,0x20b22bc3,0xaa6daadd,0x2bea23c6,0xa0b228c4,0xabeaaa6d,0x20b2a8c4,0x2bea2a6d,0xa564a95f,0x26d71a48,0x2b8829ed,0x2b3b2bfe,
  0xabfe2bfe,0xabfe2bfe,0xabfe2bfe,0xabfe2bfe,0xaadd2bea,0xa3c628c4,0x281da0b2,0x2bc3aa6d,0xa81d2bc3,0x2adda3c6,0x281dabc3,0xaadd23c6,
  0x9a482b88,0x29edab3b,0xabfe2564,0x295f26d7,0x26d72b3b,0xa6d7ab3b,0x26d72b3b,0xa6d7ab3b,0x2a6d2add,0xabeaa3c6,0x28c4a81d,0x20b22bc3,
  0x2bea2a6d,0xa0b228c4,0xabeaaa6d,0x20b2a8c4,0x2b8829ed,0x2b3b2bfe,0x2564295f,0xa6d79a48,0xabfe2bfe,0xabfe2bfe,0xabfe2bfe,0xabfe2bfe,
  0x2addabea,0x23c6a8c4,0xa81d20b2,0xabc32a6d,0xa81d2bc3,0x2adda3c6,0x281dabc3,0xaadd23c6,0x1a48ab88,0xa9ed2b3b,0x2bfea564,0xa95fa6d7,
  0x26d72b3b,0xa6d7ab3b,0x26d72b3b,0xa6d7ab3b,0xaa6daadd,0x2bea23c6,0xa8c4281d,0xa0b2abc3,0x2bea2a6d,0xa0b228c4,0xabeaaa6d,0x20b2a8c4,
  0xab88a9ed,0xab3babfe,0xa564a95f,0x26d71a48,0x3bfb3bff,0x3be53bf2,0x3bbf3bd4,0x3b873ba5,0x3bd03bfb,0x3b013b7c,0x399d3a60,0x378538bc,
  0x35173b52,0xbbc9b7c8,0xb074ba9b,0x3bfe391b,0x319e3b27,0xbbf3b979,0x363cb80a,0x3a2d3bc5,0xba093986,0x3a7eb8f8,0xbae5385f,0x3b3db77a,
  0xbabd393c,0x3bb0b699,0xbc00305b,0x3ba730d7,0xbb2a35c8,0xb8353bb2,0x3a64b1e8,0x3962bbf7,0xba90350b,0xba413bff,0x3602340e,0x3bf6bad8,
  0xac6aa5e4,0xb122af59,0xb402b294,0xb56ab4b7,0xb2deac9c,0xb7bdb5a5,0xb9b3b8d6,0xbb10ba73,0xbb96b676,0xb359bafe,0x3bec3884,0x2a163a29,
  0xbbe0b72c,0x2f27b9d6,0x3b5e3ae8,0xb91633a2,0xb941b9c9,0x38ad3a45,0xb80fbab3,0x36d23b13,0xb850ba0d,0x346f3b4a,0x1fdbbbed,0xb4ab3be8,
  0x3721bb76,0xbace3463,0xb8d13bdd,0x39ebadfb,0x3894bb98,0xb8fd281f,0xbb6a3bbd,0x2e2d3825,0x3b3f3b65,0x3ae83b16,0x3a813ab6,0x3a0d3a49,
  0x3263356a,0xad972b43,0xb5dfb359,0xb8eeb7f3,0xa9b139aa,0xbbedba25,0x3340b889,0x3b983afb,0xbaa2aa16,0xb4cfbb8e,0x3c0038ad,0xb44b38e5,
  0xbb853625,0x3bbdb4c3,0xbbe432ad,0x3bfbaf8b,0xbaacb6d2,0x39243954,0xb65fbace,0x2fbd3bb8,0xb9661648,0xba603bf8,0x383a31cf,0x3b27bbb3,
  0x3219b9eb,0xbb1836f4,0xb9903be5,0x37dd3010,0xb6c6b61a,0xb80ab76f,0xb8a8b85a,0xb93cb8f3,0xbbd7bb87,0xbbf8bbfd,0xbb71bbc9,0xba4dbaf1,
  0xbbfeb9a6,0x305bb91f,0x3bcb3a97,0xb50b37d2,0xb87abbfe,0x3ba13546,0x24523a7e,0xbbb5ba54,0xb576bb63,0x340e3ba3,0xb13bbbd3,0x2c9c3bf2,
  0x386abb3d,0xba2139f8,0x3b57b835,0xbbf13432,0x39e7bc00,0xb8d6adc9,0xbacb3bde,0x372c3457,0x3bdab962,0x3764bb35,0xb9c03122,0xbaf73bef,
  0x398b39cd,0x38fd3946,0x386538b2,0x37853815,0xba85b9c9,0xbb92bb1e,0xbbfebbdd,0xbbc2bbf5,0xb66b3682,0xbb01bb94,0x387fb371,0x3a2d3beb,
  0xbac7bb76,0x3a00ad33,0x36bb3bd4,0xbbeab79b,0xbc0026ad,0x3bf32c38,0xbbd6b109,0x3ba733eb,0x3153bbff,0xb70a3b9e,0x396bba9b,0xbade390c,
  0xb5d4b5bc,0xbbb03b2c,0x32013830,0x3bf6ba67,0x3bccbb52,0x2c06b92e,0xbb83385f,0xb8c73bab,0xb9c5b982,0xba41ba04,0xbab0ba7a,0xbb10bae1,
  0xb8a3b986,0xb52fb74e,0xa94db1e8,0x33d32e91,0xbb54bb4f,0x37bdb523,0x3a9e3bc8,0xb916308d,0x3840b5c8,0x394a3bf9,0xbb42b294,0xb0a6bb0a,
  0x251bbbff,0xaf273bfc,0x327cbbe6,0xb4ab3bc0,0x3be325e4,0xbb2fb4e7,0x39e33884,0xb81aba35,0x3b73bb78,0xb46fb715,0xbbdc3ad1,0x2e2d38cc,
  0x33283676,0x3bfcba19,0x3581bab3,0xba6b3493,0x363136dd,0x34cf3581,0x32c6341a,0x2fbd3153,0xbae1bb65,0xb970ba39,0xb715b889,0xb16cb4f3,
  0xb9a12a7a,0xb924bbfe,0x3a933042,0x37dd3bcc,0x308db9aa,0x3b453b07,0xb94632ad,0xb845bbfa,0xbb68b55e,0x3b1836bb,0xbabab805,0x3a4d38a3,
  0x3bc0b625,0xbbfe2ec3,0x3b9431cf,0xba89b742,0x9cb6b95d,0xbbf8396b,0xb1b63a5c,0x3bb5b840,0x38cc9648,0x3b81bbac,0xac38b85a,0xbbce3933,
  0xbb60bb3a,0xbba1bb83,0xbbd2bbbc,0xbbf1bbe3,0x3815361a,0x39df3907,0x3b2c3a97,0x3be23b9c,0xb9afbbfd,0x3a21294d,0x388e3bee,0xbaf7b328,
  0x3beb39a6,0xb6af37a6,0xba04bbd3,0x3ac42d00,0x360ebb89,0xb7643b42,0x3855baeb,0xb8ee3a85,0x33eb3b63,0x28e8bbf5,0xb5233bde,0x389ebb21,
  0x3c00b9f0,0x2d97b9e3,0xbbdf38db,0xb44b3ac7,0xba673c00,0x358d3487,0x3bfcbab6,0x330fba15,0x3b7a3bf1,0x394a3a93,0x33893764,0xb3d39cb6,
  0x3afb3be2,0x35eb3946,0xb4c328e8,0xbaa9b8cc,0x27763af7,0xbb2fbaba,0x3a76ad97,0x30a63b60,0xaf8b3ac4,0xb994bb94,0x3bf8358d,0xb8743815,
  0xbb4c38ee,0x3bfcb1b6,0xbad5b4cf,0x381a39af,0xbbb3389e,0x3b592c38,0xb76fb970,0xb24b3beb,0xb9d2344b,0xbb923bd2,0xb0f03924,0x3a6bb60e,
  0xb8f3330f,0xbc003b2c,0xb91f3b45,0x323233eb,0xb5b1afbd,0xba00b88e,0xbbc6bb18,0xbbc2bc00,0xb7d2b16c,0xbb6fba04,0xbba3bbfe,0xb86fba67,
  0xbbffb7dd,0x370ab855,0x38b73bf8,0xbbeab631,0xbbf2b845,0x39bcb523,0x2dc93b81,0xbaa5bae1,0xb68dba4d,0xac063bdf,0x382abba1,0xbade39a1,
  0xb457ba89,0xb6543bfc,0x3b16b9df,0xbbd8308d,0x397dbbb5,0xb52fb2c6,0xbbe73a21,0xb8c73b68,0x3a49bbce,0x2311b715,0xba2536af,0xbbd93bc0,
  0xb958b785,0xbb81ba9e,0xbbefbbf3,0xba89bb73,0xbbf7bbc2,0xb9b8bb42,0xaf59b70a,0x384a3328,0xbb8bba2d,0x39dfb27c,0x34263bb0,0xbbceb98b,
  0xb4b7bbea,0x3b6c39e3,0xbafe2c06,0x3185ba85,0xaadebba7,0xb6af3bdc,0x3a58ba41,0xbbe2366b,0x3a29bade,0xbc003581,0x3a45352f,0xb2f7bac7,
  0x3b37bbf6,0x28e8b865,0xbaee37bd,0xbac43c00,0x3b13b8c7,0x3b5cbbfe,0x3463b94a,0xb8993153,0xb9f4bb10,0xb58db87f,0x3029af27,0x389e35d4,
  0x2dfbb3d3,0x399936bb,0x3bf23b2f,0x3ac13bcc,0x3552b916,0x39703bd6,0xbbbab46f,0x330fb9c5,0x3ba530a6,0xb5f7396b,0xb7c8bbfc,0x3be138a3,
  0x3bfdb4ab,0xbb45b201,0x38e038fd,0xb16cbb54,0x391b381a,0xa17fbb83,0xb8f83b92,0x3bcfb840,0x36e82e2d,0x3bfebab0,0x37febb01,0xb845251b,
  0xb77a3a6b,0x3648294d,0x3bb2ba00,0x3a8cbbe3,0xb742b93c,0x2311b340,0x37a6340e,0x3aa93966,0x3b963a4d,0x3b7f3c00,0x380f3a21,0xb0be3219,
  0x3933b50b,0x35eb3be4,0xbbf5b8d6,0x3874b6c6,0x39413bb5,0xbbffb65f,0x38d1b764,0x33ba3bd7,0x3b9c2c9c,0xb994b83a,0x34873ae8,0x324bbbfe,
  0xb7213bf1,0x3b47b990,0xbbbf2d97,0x38c1387a,0x2d00372c,0x3b59b8a8,0x3a39bbed,0xb232b576,0xbbfb3af7,0xb9743b71,0x307434cf,0x3adbb86a,
  0x3b213a0d,0x3c003bcb,0x3b073bbd,0x386f39e7,0x351738ee,0xb599a452,0xbae5b924,0xbbe9bbda,0x3a153b98,0xbb6fb13b,0x2ec3ba60,0x3aa53b3f,
  0xba09344b,0xa884bb57,0x3a643b18,0xbbc3b263,0xb4f33bfb,0x39bcbacb,0xbbac380a,0x3bd8a9b1,0xbb2aafbd,0x36a439c0,0x3402bbf8,0xba6f3aa2,
  0xbbfa3b27,0xb6543a81,0x3907b05b,0x3bd9bb85,0x2c6ab7dd,0xb9da35df,0xbbec3ba1,0xb8203aac,0x3bf53b87,0x3b6c3bec,0x392e3a7e,0x32f73721,
  0xb9e7b785,0xbbfcbb5e,0xba81bbb0,0xb43eb894,0x379b3bfe,0xbc00b80f,0x374eb835,0x38993bfb,0xbb3fba2d,0x3b329fdb,0xb3403a41,0xb8eabbd0,
  0xb90c3b3d,0x3b5cb8d1,0xbbf93122,0x3ac13517,0x29b1bba7,0xb94f3b6a,0x3be4b7bd,0xbaf4b19e,0xbbab3962,0xb9993bbf,0x34e73359,0x3be1ba09,
  0x3b85bbf6,0x353ab99d,0xb83a2f27,0xbbf03abd,0x2e91356a,0xb5f7b074,0xba19b8ad,0xbbcfbb2a,0xb966bb10,0xaba7b63c,0x38a8346f,0x3bb73a90,
  0xbb0aaa16,0xa17fbae5,0x3b1e3ace,0xba8c2c6a,0x36c6b916,0x36ff3c00,0xbbcbb8fd,0x3a50b2de,0xba35b6d2,0x36483a64,0x2d33bbe5,0xb84a3b96,
  0x3bfeb4ab,0xb9fcb602,0x313b3b01,0x37e8bbe0,0x3493b9eb,0xb9b83402,0xbb9e3bc9,0xb1853941,0x35762e2d,0x3b90b9b3,0x3acbbbf3,0x2fefb850,
  0x3a543bcf,0x2884374e,0xb9f8b648,0xbbe9bbab,0x398b3bb7,0xb4db3340,0xbbdcb9fc,0xb911bb85,0xb4323a8c,0xb6a4bbf9,0x3b3539b8,0xbbc3ae91,
  0xb66b3a50,0xad65bbe4,0x38653b90,0xbb0db966,0xbbef384a,0x39da34e7,0x2b43bb6c,0xba6f3b0a,0xbc0037e8,0x3759383a,0x387fbbfc,0xbbf636c6,
  0xb7f33185,0xbb7f3a19,0xbb8e3c00,0xb8203a35,0xb5d42fef,0xba1d38a8,0xbbd63b32,0xbba93bfe,0xb8e5b2f7,0xbbffbb1e,0xb954bb5c,0x30beb493,
  0xb9c5b43e,0xbb9fbbcb,0xb201b94f,0x3a313576,0xbbb8b899,0x3b47ad33,0xb6f43999,0xb3babbf5,0xbb54b8ea,0x3bf9313b,0xbab0353a,0x3790b9e7,
  0xb010bac1,0xb9743b9e,0x3bfdb5f7,0xb8c1b79b,0x251bbaf4,0xbb1b3acb,0x3a9e2ba7,0x2e5fbb3f,0x3af1bbe1,0x3599b92e,0xb546a17f,0xbadb390c,
  0x3b73bbf0,0x3929ba81,0x327cb6ff,0xb49f29b1,0xb825baa9,0x353aaec3,0x3b7c3994,0x3af43bfa,0x360eb0be,0x3bf43a64,0x388e3b47,0xb7372c6a,
  0x38bcb874,0x2ba73bac,0xb979bb59,0x3bf03742,0x3c0033ba,0xbb043402,0x3855b974,0xacce3b96,0x3bc5b24b,0xb6ffb907,0xb6993c00,0x3bb7b933,
  0x363138c1,0x3902bbec,0xbbdf3599,0x34ff3941,0x30d73232,0x39fcb7a6,0x3bffbb6f,0x3a50bb9c,0xb9a13adb,0xb47b380f,0x32c62884,0x3937b721,
  0x3ad8386f,0x3b903bf5,0x35a539bc,0xb7e8ad00,0x3b683be9,0x2ef538d1,0xba93b6a4,0xbb24bbfb,0x3a733aa5,0xbbfcb487,0x39d6b654,0xafef3b21,
  0x1cb63bc3,0xb7b2bbbf,0x3aba39da,0xbbfab517,0xb3a23bd8,0x3b32ba39,0xbb4a2311,0x343e3a15,0xbb603a6f,0x3a3d3074,0x31b6bb7f,0xbb9a3a09,
  0xbbe83bd9,0xb94f3b07,0xa81f35eb,0x38eab4f3,0xb9af3820,0xbbae3ae5,0xbbd23bff,0xba113b2a,0x319e389e,0xb929b426,0xbc00bb45,0xb911bb37,
  0xbbffbac1,0xb805bafe,0x382a217f,0x3bfd3b13,0xbabd330f,0x34dbba58,0x36023bfe,0xbb0db9f4,0xb68dbbe1,0x3a5c3a45,0xbbe7b648,0x3b89adfb,
  0xba90b16c,0x2d653aee,0x39b3bb81,0xbbf63552,0x397dbbcf,0xbbbc3463,0x338939b8,0x39f0bba5,0x32deb845,0xb7593029,0xbb5e39df,0xbba93bfd,
  0x3b7aba8c,0x3beebbf2,0x3a76bb6c,0x36ddb91b,0xbbe0ba89,0xba1dbbba,0x1fdbb6af,0x3a3136e8,0xa776b84a,0x3aeb37c8,0x3ad53c00,0xaa7a377a,
  0xb850bbce,0x3b9f38e0,0xbb6a28e8,0x3790b958,0x3b4cb185,0xb8db38f8,0x30f0bb5c,0x355e3bf7,0x3894bbe2,0xbbf937fe,0x399d358d,0x2e5fbb8b,
  0x39d232f7,0x341abbb2,0xbbc63999,0x395d34b7,0x3bd0bac4,0x3b1bbbef,0x363cb970,0xb49faade,0xb5b13899,0x30422f59,0x38b7b5f7,0x3b3aba29,
  0x3219b3d3,0x3b0438b7,0x3b713bfc,0x34ff397d,0x36e83aa9,0xb8b2adc9,0xbbefbb59,0xb5bcba49,0x3bd730a6,0xb902382a,0xa452bb92,0x39373b7a,
  0xb9583874,0x3371bb16,0x34263c00,0xb982bafb,0x387a381a,0x347bbbe7,0xbb573a00,0x3b242776,0xbb8b324b,0x31093a25,0x3a58bb6f,0xbb4f2f8b,
  0xb86a3a6b,0x2ef53389,0x39c0b70a,0x3bfabb4c,0xaadeb232,0xb83034c3,0xbaee39bc,0xbbff3bb3,0x3bda3bc2,0x37b23a76,0xb5df2c06,0xbb9ab9d2,
  0xbb37b86f,0xba7abbf8,0x3029b654,0x3b7838f3,0x32633bea,0xba3dbad5,0x3c00352f,0xba1135b1,0xb9f4baa5,0x3bc8376f,0xbbba2311,0x39cdb7d2,
  0xbaa23ade,0x3baeb0f0,0xb65fb94a,0xb7373bff,0x3552bbd8,0xbbe6391f,0x38e035eb,0x3682bbf2,0xbaac38c7,0xbbf43bc6,0xb9903b2f,0xacce368d,
  0x3bfdbbd9,0x3ad1bba3,0x37feb994,0x26adb457,0x38a33b9a,0xb8dba452,0xbb83bbae,0x2a7ab86a,0x37423b78,0xbab6b426,0xb907bbe6,0x39aa2ade,
  0xb8403a11,0x341abb57,0x294d3bf4,0xb55ebbda,0xb93339cd,0x3889ba58,0xb7a63ad1,0x3625bb37,0xbbe33737,0x304239c0,0x3b42bb04,0xb95db263,
  0xbb9c3682,0xb2ad3aee,0x3bf5b8b2,0x1648b9f4,0xb3282cce,0xb80535df,0xb9e33902,0xbb3a3aa2,0xad0026ad,0xb1cf3029,0xb4873371,0xb61a3552,
  0xba85b4ff,0xba5cbc00,0x3581b47b,0x3bfd3aac,0xbb21b5bc,0xb85abbba,0x3a393109,0x39a63bfd,0xbac7b937,0x3bbc365f,0xbbfeaef5,0x3b89b219,
  0xba15b982,0x3a9738e0,0xbb07b830,0x3b6336e8,0x3153bb24,0xbbee3990,0x36bb37b2,0x39f0bbd7,0x34f3bb4f,0xbbd337fe,0xaec33a7a,0x3c00b958,
  0x3bccbbfa,0x3aebbb71,0x396bba3d,0x36ddb87a,0x3bfabbff,0x3bdebbef,0x3bacbbc8,0x3b65bb8b,0x3bc03911,0x38303b6a,0xb946ad65,0xbb4fbbd0,
  0x3a353bfd,0xb85f30f0,0xbb1ebbbc,0x35c8b5b1,0x38cc3b0d,0xba7ab99d,0x3b943759,0xbbffb19e,0xb4933b89,0x31e8bbc6,0xad333bee,0xa5e4bbff,
  0xb8153bf6,0x3bc8b63c,0xac38ba1d,0xbb783abd,0xbbf539f0,0x329438b7,0x3b9ebaeb,0xb676b68d,0xbbeb3ba9,0xbbe63c00,0xbb2c3b9f,0xb9cd3a90,
  0xb79b36dd,0xb884382a,0xb92e38db,0xb9c9397d,0x33eb3a31,0xbad1b602,0xba04bbf9,0x3682b2de,0xb90c2a7a,0xbab3bbe7,0x374eb41a,0x3b763b7a,
  0xba673790,0x38b2b9b3,0xb5233b1b,0x26adbbe0,0xbbabb55e,0x3bdd3389,0xbbf9b042,0x3bff2776,0xbae12e5f,0xb3713b5e,0x3bfcb929,0xb5bcb850,
  0xae91b95d,0xbbd43a76,0x34e73805,0x3b52bb4c,0x308db49f,0xb1091fdb,0xb71534db,0xb9823894,0x3b0abb3a,0x3a9bbad5,0x3a19ba5c,0x3986b9d2,
  0x2f8bb7e8,0x3bde3979,0x376f3b32,0xb9aab0d7,0x3bb83b24,0xb1223855,0xbbfdba3d,0xaa16b9a1,0x3bb3afef,0xbab63699,0x391fb94f,0xb6253ad8,
  0x30103bfa,0xb359bbdf,0x35463bae,0xb6d2bb68,0x38f3343e,0x3889bbff,0xbba3353a,0x96483a73,0xbaf13b9a,0x38ad32c6,0x39f8bbf4,0xb9eb9cb6,
  0xb7d238ea,0xb2ad35a5,0x2dc92ba7,0x361ab3a2,0xba543a11,0xbace3a93,0xbb353b04,0xbb873b60,0x3bf23af4,0x31cf39d6,0xbb16b6ff,0xb9a6bbe8,
  0xb4323737,0xbbe5baba,0x2b43b902,0x3bfe39af,0x34573bf0,0xb85abb4a,0x3a2539fc,0xbb63b825,0xbbef2cce,0x3bc9b1b6,0xbb8e347b,0x3b3db60e,
  0xba493bb7,0x3a97a81f,0x34c3bb90,0xbc0038bc,0xb7f3b4ff,0xba7e3bd2,0x39542ef5,0x3962bc00,0xbafb3a50,0xbbd33b7c,0xbbf83bfc,0xbb653bc5,
  0x38e5b937,0x3835b88e,0x36f4b7b2,0x356ab631,0xbb13bbe9,0x31e8b6f4,0x3bf239da,0x36763af1,0x3be83911,0x340e3ab0,0xbb7cb759,0xb72cbb73,
  0x2dfbbbc3,0x32943bfd,0xb7c8bb7f,0x39c93a54,0x38253b0d,0xb8d6ba9e,0x39793a1d,0xba0db98b,0x3ba5ba6f,0xb884b546,0xb8f83bff,0x3b76b432,
  0xb8bc3bf6,0x3ae8b27c,0x3699bb9f,0xbb98366b,0x391bb820,0x3ab3b9f8,0x3bb2bb47,0x3bffbbef,0xbbc53ba9,0xbbed3bdc,0xbbff3bf9,0xbbfb3c00,
  0x377ab0be,0x3bdd3b35,0x2f593974,0xbb52b7f3,0x30d73a31,0xbbbdb865,0xb5a5bb1b,0x3b2735d4,0x3bf733ba,0xbbd42b43,0x3afeb599,0xb98638e5,
  0xbad83790,0x3a60b87f,0xb9d63929,0x393cb9c5,0x34b738c1,0x3a9bbb8e,0xba45a884,0xb5c83bb8,0xba732e5f,0xb80a3bd6,0x3b4ab4db,0x350bbb54,
  0xba293adb,0xb85f3954,0xb46336a4,0x25e43010,0x33a2b49f,0x305bb201,0x281fad65,0xac9c251b,0x3f803f80,0x3f803f80,0x3f803f80,0x3f803f80,
  0x3f803f80,0x3f803f80,0x3f803f80,0x3f803f80,0x3f803f80,0x3f803f80,0x3f803f80,0x3f803f80,0x3f803f80,0x3f803f80,0x3f803f80,0x3f803f80,
  0x3f803f80,0x3f803f80,0x3f803f80,0x3f803f80,0x3f803f80,0x3f803f80,0x3f803f80,0x3f803f80,0x3f803f80,0x3f803f80,0x3f803f80,0x3f803f80,
  0x3f803f80,0x3f803f80,0x3f803f80,0x3f803f80,0x3f803f80,0x3f803f80,0x3f803f80,0x3f803f80,0x3f803f80,0x3f803f80,0x3f803f80,0x3f803f80,
  0x3f803f80,0x3f803f80,0x3f803f80,0x3f803f80,0x3f803f80,0x3f803f80,0x3f803f80,0x3f803f80,0x3f803f80,0x3f803f80,0x3f803f80,0x3f803f80,
  0x3f803f80,0x3f803f80,0x3f803f80,0x3f803f80,0x3f803f80,0x3f803f80,0x3f803f80,0x3f803f80,0x3f803f80,0x3f803f80,0x3f803f80,0x3f803f80,
  0x3f803f80,0x3f803f80,0x3f803f80,0x3f803f80,0x3f803f80,0x3f803f80,0x3f803f80,0x3f803f80,0x3f803f80,0x3f803f80,0x3f803f80,0x3f803f80,
  0x3f803f80,0x3f803f80,0x3f803f80,0x3f803f80,0x3f803f80,0x3f803f80,0x3f803f80,0x3f803f80,0x3f803f80,0x3f803f80,0x3f803f80,0x3f803f80,
  0x3f803f80,0x3f803f80,0x3f803f80,0x3f803f80,0x3f803f80,0x3f803f80,0x3f803f80,0x3f803f80,0x3f803f80,0x3f803f80,0x3f803f80,0x3f803f80,
  0x3f803f80,0x3f803f80,0x3f803f80,0x3f803f80,0x3f803f80,0x3f803f80,0x3f803f80,0x3f803f80,0x3f803f80,0x3f803f80,0x3f803f80,0x3f803f80,
  0x3f803f80,0x3f803f80,0x3f803f80,0x3f803f80,0x3f803f80,0x3f803f80,0x3f803f80,0x3f803f80,0x3f803f80,0x3f803f80,0x3f803f80,0x3f803f80,
  0x3f803f80,0x3f803f80,0x3f803f80,0x3f803f80,0x3f803f80,0x3f803f80,0x3f803f80,0x3f803f80,0x3f803f80,0x3f803f80,0x3f803f80,0x3f803f80,
  0x3f803f80,0x3f803f80,0x3f803f80,0x3f803f80,0x3f803f80,0x3f803f80,0x3f803f80,0x3f803f80,0x3f803f80,0x3f803f80,0x3f803f80,0x3f803f80,
  0x3f803f80,0x3f803f80,0x3f803f80,0x3f803f80,0x3f803f80,0x3f803f80,0x3f803f80,0x3f803f80,0x3f803f80,0x3f803f80,0x3f803f80,0x3f803f80,
  0x3f803f80,0x3f803f80,0x3f803f80,0x3f803f80,0x3f803f80,0x3f803f80,0x3f803f80,0x3f803f80,0x3f803f80,0x3f803f80,0x3f803f80,0x3f803f80,
  0x3f803f80,0x3f803f80,0x3f803f80,0x3f803f80,0x3f803f80,0x3f803f80,0x3f803f80,0x3f803f80,0x3f803f80,0x3f803f80,0x3f803f80,0x3f803f80,
  0x3f803f80,0x3f803f80,0x3f803f80,0x3f803f80,0x3f803f80,0x3f803f80,0x3f803f80,0x3f803f80,0x3f803f80,0x3f803f80,0x3f803f80,0x3f803f80,
  0x3f803f80,0x3f803f80,0x3f803f80,0x3f803f80,0x3f803f80,0x3f803f80,0x3f803f80,0x3f803f80,0x3f803f80,0x3f803f80,0x3f803f80,0x3f803f80,
  0x3f803f80,0x3f803f80,0x3f803f80,0x3f803f80,0x3f803f80,0x3f803f80,0x3f803f80,0x3f803f80,0x3f803f80,0x3f803f80,0x3f803f80,0x3f803f80,
  0x3f803f80,0x3f803f80,0x3f803f80,0x3f803f80,0x3f803f80,0x3f803f80,0x3f803f80,0x3f803f80,0x3f803f80,0x3f803f80,0x3f803f80,0x3f803f80,
  0x3f803f80,0x3f803f80,0x3f803f80,0x3f803f80,0x3f803f80,0x3f803f80,0x3f803f80,0x3f803f80,0x3f803f80,0x3f803f80,0x3f803f80,0x3f803f80,
  0x3f803f80,0x3f803f80,0x3f803f80,0x3f803f80,0x3f803f80,0x3f803f80,0x3f803f80,0x3f803f80,0x3f803f80,0x3f803f80,0x3f803f80,0x3f803f80,
  0x3f803f80,0x3f803f80,0x3f803f80,0x3f803f80,0x3f803f80,0x3f803f80,0x3f803f80,0x3f803f80,0x3f803f80,0x3f803f80,0x3f803f80,0x3f803f80,
  0x3f803f80,0x3f803f80,0x3f803f80,0x3f803f80,0x3f803f80,0x3f803f80,0x3f803f80,0x3f803f80,0x3f803f80,0x3f803f80,0x3f803f80,0x3f803f80,
  0x3f803f80,0x3f803f80,0x3f803f80,0x3f803f80,0x3f803f80,0x3f803f80,0x3f803f80,0x3f803f80,0x3f803f80,0x3f803f80,0x3f803f80,0x3f803f80,
  0x3f803f80,0x3f803f80,0x3f803f80,0x3f803f80,0x3f803f80,0x3f803f80,0x3f803f80,0x3f803f80,0x3f803f80,0x3f803f80,0x3f803f80,0x3f803f80,
  0x3f803f80,0x3f803f80,0x3f803f80,0x3f803f80,0x3f803f80,0x3f803f80,0x3f803f80,0x3f803f80,0x3f803f80,0x3f803f80,0x3f803f80,0x3f803f80,
  0x3f803f80,0x3f803f80,0x3f803f80,0x3f803f80,0x3f803f80,0x3f803f80,0x3f803f80,0x3f803f80,0x3f803f80,0x3f803f80,0x3f803f80,0x3f803f80,
  0x3f803f80,0x3f803f80,0x3f803f80,0x3f803f80,0x3f803f80,0x3f803f80,0x3f803f80,0x3f803f80,0x3f803f80,0x3f803f80,0x3f803f80,0x3f803f80,
  0x3f803f80,0x3f803f80,0x3f803f80,0x3f803f80,0x3f803f80,0x3f803f80,0x3f803f80,0x3f803f80,0x3f803f80,0x3f803f80,0x3f803f80,0x3f803f80,
  0x3f803f80,0x3f803f80,0x3f803f80,0x3f803f80,0x3f803f80,0x3f803f80,0x3f803f80,0x3f803f80,0x3f803f80,0x3f803f80,0x3f803f80,0x3f803f80,
  0x3f803f80,0x3f803f80,0x3f803f80,0x3f803f80,0x3f803f80,0x3f803f80,0x3f803f80,0x3f803f80,0x3f803f80,0x3f803f80,0x3f803f80,0x3f803f80,
  0x3f803f80,0x3f803f80,0x3f803f80,0x3f803f80,0x3f803f80,0x3f803f80,0x3f803f80,0x3f803f80,0x3f803f80,0x3f803f80,0x3f803f80,0x3f803f80,
  0x3f803f80,0x3f803f80,0x3f803f80,0x3f803f80,0x3f803f80,0x3f803f80,0x3f803f80,0x3f803f80,0x3f803f80,0x3f803f80,0x3f803f80,0x3f803f80,
  0x3f803f80,0x3f803f80,0x3f803f80,0x3f803f80,0x3f803f80,0x3f803f80,0x3f803f80,0x3f803f80,0x3f803f80,0x3f803f80,0x3f803f80,0x3f803f80,
  0x3f803f80,0x3f803f80,0x3f803f80,0x3f803f80,0x3f803f80,0x3f803f80,0x3f803f80,0x3f803f80,0x3f803f80,0x3f803f80,0x3f803f80,0x3f803f80,
  0x3f803f80,0x3f803f80,0x3f803f80,0x3f803f80,0x3f803f80,0x3f803f80,0x3f803f80,0x3f803f80,0x3f803f80,0x3f803f80,0x3f803f80,0x3f803f80,
  0x3f803f80,0x3f803f80,0x3f803f80,0x3f803f80,0x3f803f80,0x3f803f80,0x3f803f80,0x3f803f80,0x3f803f80,0x3f803f80,0x3f803f80,0x3f803f80,
  0x3f803f80,0x3f803f80,0x3f803f80,0x3f803f80,0x3f803f80,0x3f803f80,0x3f803f80,0x3f803f80,0x3f803f80,0x3f803f80,0x3f803f80,0x3f803f80,
  0x3f803f80,0x3f803f80,0x3f803f80,0x3f803f80,0x3f803f80,0x3f803f80,0x3f803f80,0x3f803f80,0x3f803f80,0x3f803f80,0x3f803f80,0x3f803f80,
  0x3f803f80,0x3f803f80,0x3f803f80,0x3f803f80,0x3f803f80,0x3f803f80,0x3f803f80,0x3f803f80,0x3f803f80,0x3f803f80,0x3f803f80,0x3f803f80,
  0x3f803f80,0x3f803f80,0x3f803f80,0x3f803f80,0x3f803f80,0x3f803f80,0x3f803f80,0x3f803f80,0x3f803f80,0x3f803f80,0x3f803f80,0x3f803f80,
  0x3f803f80,0x3f803f80,0x3f803f80,0x3f803f80,0x3f803f80,0x3f803f80,0x3f803f80,0x3f803f80,0x3f803f80,0x3f803f80,0x3f803f80,0x3f803f80,
  0x3f803f80,0x3f803f80,0x3f803f80,0x3f803f80,
};

__device__ __align__(128) float    g_part[16][8][2176];
__device__ __align__(128) float    g_kv[16][2176];
__device__ __align__(128) uint4    g_o[16 * 16 * 1024];
__device__ __align__(128) uint4    g_h16[128 * 2048];
__device__ __align__(128) unsigned g_ocnt[2 * 16 * 32];
__device__ unsigned g_epoch[128];
#define GSTAMP(role, i) do {} while (0)
#define STAMP(role, i) do {} while (0)
#define PDUMP(role) do {} while (0)
#define PROF_SMEM 0

constexpr int STAGE_BYTES = 57344;
constexpr int OFF_H = 2 * 16384, OFF_PK = 4 * 16384, OFF_VP = 9 * 16384, OFF_SPARE = 10 * 16384;
constexpr int OFF_XT = 172032, XT_STRIDE = 4112;
constexpr int OFF_BAR = 204928, OFF_EPOCH = OFF_BAR + 640, OFF_EX = OFF_BAR + 656, OFF_D = OFF_BAR + 672, OFF_SCALE = OFF_BAR + 704, OFF_TAP = OFF_BAR + 768;
constexpr int OFF_F2F = 205824, OFF_F2I = 207872, OFF_F4 = 209920, OFF_ONES = 214016, OFF_KVB = 214016;
constexpr int OFF_STG = 219136, STG_STRIDE = 4352, SMEM_TOTAL = 232192 + PROF_SMEM;
enum { B_FULL1 = 0, B_EMPTY1 = 3, B_Q = 6, B_ODONE1 = 7, B_O1RDY = 8, B_H = 9, B_XRAW = 10, B_XT = 11, B_KV = 12, B_Y = 13, B_PKFREE = 14, B_AFREE = 15,
       B_STG = 18, B_ODONE = 24, B_XFREE = 25, B_FULL2 = 33, B_CONS2 = 49, B_COUNT = 62 };
__host__ __device__ constexpr int bar_count(int i) {
  return i < B_EMPTY1 ? 1 : i < B_Q ? 4 : i == B_XT ? 4 : i == B_KV ? 2 : i == B_Y ? 9 : i == B_PKFREE ? 8
       : (i >= B_AFREE && i < B_STG) ? 16 : (i == B_ODONE || i == B_ODONE1) ? 8 : (i >= B_XFREE && i < B_FULL2) ? 4
       : (i >= B_CONS2 && i <= B_CONS2 + 10) ? 4 : i >= B_CONS2 ? 2 : (i >= B_FULL2 && i < B_FULL2 + 7) ? 2 : 1;
}
__host__ __device__ constexpr uint64_t bar_counts(int r) {
  uint64_t v = 0;
  for (int w = 0; w < 11; w++) v |= (uint64_t)(bar_count(1 + 11 * r + w) - 1) << (4 * w);
  return v;
}
constexpr uint64_t SLOT_A = 0x9023190231902392ull;
constexpr uint64_t SLOT_B = 0x7654876548765410ull;
constexpr int SPIN_LIMIT = 1 << 22;
#define PKV CU_TENSOR_MAP_L2_PROMOTION_L2_128B
#define BPRE B_KV
#define PFD 3
#define PD1 400
#define PD2 100
#define E1C 2
#define OSP 4
#define QPF 8
#define TSPLIT 1
#define OC0 2
#define OC1 2
#define BSPL 4
#define BPACE 300
#define NPOS 0
#define O1POS 1
#define HL1 4
#define OCH 3
#define O1D 3
#define QPOS 2
#define HOLD2 13
#define A0COL 0
#define BSTART 600
#define HSTART 2000
#define PACE 2000
#define OC 1

__device__ __forceinline__ uint32_t smem_u32(const void* p) { return (uint32_t)__cvta_generic_to_shared(p); }
__device__ __forceinline__ void wg_fence() { asm volatile("wgmma.fence.sync.aligned;" ::: "memory"); }
__device__ __forceinline__ void wg_commit() { asm volatile("wgmma.commit_group.sync.aligned;" ::: "memory"); }
template <int N> __device__ __forceinline__ void wg_wait() { asm volatile("wgmma.wait_group.sync.aligned %0;" ::"n"(N) : "memory"); }
template <int N> __device__ __forceinline__ void keep(float (&d)[N]) {
#pragma unroll
  for (int i = 0; i < N; i++) asm volatile("" : "+f"(d[i])::"memory");
}
__device__ __forceinline__ uint64_t mkdesc(uint32_t addr, uint32_t lbo, uint32_t sbo, uint32_t swz) {
  uint32_t lo = ((addr & 0x3FFFF) >> 4) | ((lbo >> 4) << 16), hi = (sbo >> 4) | (swz << 30);
  return ((uint64_t)hi << 32) | lo;
}
__device__ __forceinline__ void mbar_init(uint32_t bar, int cnt) { asm volatile("mbarrier.init.shared::cta.b64 [%0], %1;" ::"r"(bar), "r"(cnt)); }
__device__ __forceinline__ void mbar_expect(uint32_t bar, int bytes) { asm volatile("mbarrier.arrive.expect_tx.shared::cta.b64 _, [%0], %1;" ::"r"(bar), "r"(bytes) : "memory"); }
__device__ __forceinline__ void mbar_arrive(uint32_t bar) { asm volatile("mbarrier.arrive.shared::cta.b64 _, [%0];" ::"r"(bar) : "memory"); }
__device__ __forceinline__ void mbar_arrive_cl(uint32_t bar, uint32_t cta) {
  asm volatile("{\n.reg .b32 r;\nmapa.shared::cluster.u32 r, %0, %1;\nmbarrier.arrive.shared::cluster.b64 _, [r];\n}\n" ::"r"(bar), "r"(cta) : "memory");
}
__device__ __forceinline__ void mbar_wait(uint32_t bar, uint32_t parity) {
  asm volatile("{\n.reg .pred p;\n.reg .u32 n;\nmov.u32 n, 0;\n"
               "W_%=:\nmbarrier.try_wait.parity.shared::cta.b64 p, [%0], %1;\n@p bra D_%=;\n"
               "add.u32 n, n, 1;\nsetp.lt.u32 p, n, %2;\n@p bra W_%=;\ntrap;\nD_%=:\n}\n" ::"r"(bar), "r"(parity), "n"(SPIN_LIMIT) : "memory");
}
__device__ __forceinline__ void fence_async() { asm volatile("fence.proxy.async.shared::cta;" ::: "memory"); }
__device__ __forceinline__ void bar_sync(int id) { asm volatile("bar.sync %0, 128;" ::"r"(id) : "memory"); }
__device__ __forceinline__ void tma2d(uint32_t dst, const CUtensorMap* m, int c0, int c1, uint32_t bar) {
  asm volatile("cp.async.bulk.tensor.2d.shared::cluster.global.mbarrier::complete_tx::bytes [%0], [%1, {%3, %4}], [%2];"
               ::"r"(dst), "l"(m), "r"(bar), "r"(c0), "r"(c1) : "memory");
}
__device__ __forceinline__ void tma2d_mc(uint32_t dst, const CUtensorMap* m, int c0, int c1, uint32_t bar) {
  asm volatile("cp.async.bulk.tensor.2d.shared::cluster.global.mbarrier::complete_tx::bytes.multicast::cluster [%0], [%1, {%3, %4}], [%2], %5;"
               ::"r"(dst), "l"(m), "r"(bar), "r"(c0), "r"(c1), "h"((uint16_t)3) : "memory");
}
__device__ __forceinline__ void tma3d(uint32_t dst, const CUtensorMap* m, int c0, int c1, int c2, uint32_t bar) {
  asm volatile("cp.async.bulk.tensor.3d.shared::cluster.global.mbarrier::complete_tx::bytes [%0], [%1, {%3, %4, %5}], [%2];"
               ::"r"(dst), "l"(m), "r"(bar), "r"(c0), "r"(c1), "r"(c2) : "memory");
}
__device__ __forceinline__ void tma4d(uint32_t dst, const CUtensorMap* m, int c0, int c1, int c2, int c3, uint32_t bar) {
  asm volatile("cp.async.bulk.tensor.4d.shared::cluster.global.mbarrier::complete_tx::bytes [%0], [%1, {%3, %4, %5, %6}], [%2];"
               ::"r"(dst), "l"(m), "r"(bar), "r"(c0), "r"(c1), "r"(c2), "r"(c3) : "memory");
}
__device__ __forceinline__ void bulk_ld(uint32_t dst, const void* src, int bytes, uint32_t bar) {
  asm volatile("cp.async.bulk.shared::cluster.global.mbarrier::complete_tx::bytes [%0], [%1], %2, [%3];" ::"r"(dst), "l"(src), "r"(bytes), "r"(bar) : "memory");
}
__device__ __forceinline__ void bulk_ld_mc(uint32_t dst, const void* src, int bytes, uint32_t bar) {
  asm volatile("cp.async.bulk.shared::cluster.global.mbarrier::complete_tx::bytes.multicast::cluster [%0], [%1], %2, [%3], %4;"
               ::"r"(dst), "l"(src), "r"(bytes), "r"(bar), "h"((uint16_t)3) : "memory");
}
__device__ __forceinline__ void tma2d_st(const CUtensorMap* m, uint32_t src, int c0, int c1) {
  asm volatile("cp.async.bulk.tensor.2d.global.shared::cta.bulk_group [%0, {%2, %3}], [%1];" ::"l"(m), "r"(src), "r"(c0), "r"(c1) : "memory");
}
__device__ __forceinline__ void pf_l2(const void* p, int bytes) { asm volatile("cp.async.bulk.prefetch.L2.global [%0], %1;" ::"l"(p), "r"(bytes) : "memory"); }
__device__ __forceinline__ void pf_t2d(const CUtensorMap* m, int c0, int c1) {
  asm volatile("cp.async.bulk.prefetch.tensor.2d.L2.global [%0, {%1, %2}];" ::"l"(m), "r"(c0), "r"(c1) : "memory");
}
__device__ __forceinline__ void pf_t3d(const CUtensorMap* m, int c0, int c1, int c2) {
  asm volatile("cp.async.bulk.prefetch.tensor.3d.L2.global [%0, {%1, %2, %3}];" ::"l"(m), "r"(c0), "r"(c1), "r"(c2) : "memory");
}
__device__ __forceinline__ void ldsm4(uint32_t (&r)[4], uint32_t a) {
  asm volatile("ldmatrix.sync.aligned.m8n8.x4.shared.b16 {%0,%1,%2,%3}, [%4];" : "=r"(r[0]), "=r"(r[1]), "=r"(r[2]), "=r"(r[3]) : "r"(a) : "memory");
}
__device__ __forceinline__ void ldsm4t(uint32_t (&r)[4], uint32_t a) {
  asm volatile("ldmatrix.sync.aligned.m8n8.x4.trans.shared.b16 {%0,%1,%2,%3}, [%4];" : "=r"(r[0]), "=r"(r[1]), "=r"(r[2]), "=r"(r[3]) : "r"(a) : "memory");
}
__device__ __forceinline__ void stsm4(uint32_t a, uint32_t r0, uint32_t r1, uint32_t r2, uint32_t r3) {
  asm volatile("stmatrix.sync.aligned.m8n8.x4.shared.b16 [%0], {%1,%2,%3,%4};" ::"r"(a), "r"(r0), "r"(r1), "r"(r2), "r"(r3) : "memory");
}
__device__ __forceinline__ uint32_t pk2(float lo, float hi) { uint32_t r; asm("cvt.rn.bf16x2.f32 %0, %1, %2;" : "=r"(r) : "f"(hi), "f"(lo)); return r; }
__device__ __forceinline__ uint32_t hmul(uint32_t a, uint32_t b) { uint32_t r; asm("mul.rn.bf16x2 %0, %1, %2;" : "=r"(r) : "r"(a), "r"(b)); return r; }
__device__ __forceinline__ uint32_t hadd(uint32_t a, uint32_t b) { uint32_t r; asm("add.rn.bf16x2 %0, %1, %2;" : "=r"(r) : "r"(a), "r"(b)); return r; }
__device__ __forceinline__ uint32_t hmax(uint32_t a, uint32_t b) { uint32_t r; asm("max.bf16x2 %0, %1, %2;" : "=r"(r) : "r"(a), "r"(b)); return r; }
__device__ __forceinline__ uint32_t hmin(uint32_t a, uint32_t b) { uint32_t r; asm("min.bf16x2 %0, %1, %2;" : "=r"(r) : "r"(a), "r"(b)); return r; }
__device__ __forceinline__ uint32_t hmaxabs(uint32_t a, uint32_t b) { uint32_t r; asm("max.xorsign.abs.bf16x2 %0, %1, %2;" : "=r"(r) : "r"(a), "r"(b)); return r; }
__device__ __forceinline__ float ex2(float x) { float r; asm("ex2.approx.ftz.f32 %0, %1;" : "=f"(r) : "f"(x)); return r; }
__device__ __forceinline__ float rcp_fast(float x) { float r; asm("rcp.approx.ftz.f32 %0, %1;" : "=f"(r) : "f"(x)); return r; }
__device__ __forceinline__ uint32_t phi2(float lo, float hi) {
  uint32_t t;
  asm("cvt.rn.relu.bf16x2.f32 %0, %1, %2;" : "=r"(t) : "f"(hi), "f"(lo));
  const uint32_t e = pk2(ex2(lo * 1.4426950408889634f), ex2(hi * 1.4426950408889634f));
  return hadd(hadd(t, hmin(e, 0x3F803F80u)), 0x35863586u);
}
__device__ __forceinline__ bool opaque_true() { uint32_t v; asm volatile("mov.u32 %0, %%nctaid.y;" : "=r"(v)); return v != 0; }
__device__ __forceinline__ int normalise(uint32_t (&v)[32], float fd) {
  const float f0 = fd + __uint_as_float(v[0] << 16);
  uint32_t m[4] = {hmaxabs(__float_as_uint(f0) >> 16, v[0]), v[1], v[2], v[3]};
#pragma unroll
  for (int i = 4; i < 32; i++) m[i & 3] = hmaxabs(m[i & 3], v[i]);
  m[0] = hmaxabs(hmaxabs(m[0], m[1]), hmaxabs(m[2], m[3]));
  const int e = min(max((int)(__reduce_max_sync(~0u, max(m[0] & 0x7FFFu, (m[0] >> 16) & 0x7FFFu)) >> 7), 1), 253);
  if (e > 141) {
#pragma unroll
    for (int i = 0; i < 32; i++) v[i] = hmul(v[i], 0x07000700u);
  }
  const uint32_t sc = (e > 141 ? 255 - e : 142 - e) * 0x00800080u;
#pragma unroll
  for (int i = 0; i < 32; i++) {
    const uint32_t a = hmul(v[i], sc);
    v[i] = (a & 0x0FFF0FFFu) * 7 + a;
  }
  v[0] = __byte_perm(v[0], __half_as_ushort(__float2half_rn(f0 * __uint_as_float((254 - e) << 23))), 0x3254);
  return e;
}
__device__ __forceinline__ void poll_ge(const unsigned* p, unsigned target) {
#pragma unroll 1
  for (int n = 0; n < SPIN_LIMIT; n++) {
    unsigned v;
    asm volatile("ld.relaxed.gpu.global.u32 %0, [%1];" : "=r"(v) : "l"(p) : "memory");
    if (__all_sync(~0u, (int)(v - target) >= 0)) { asm volatile("fence.acquire.gpu;" ::: "memory"); return; }
  }
  __trap();
}

__device__ __forceinline__ bool elect_one() {
  uint32_t p;
  asm volatile("{\n.reg .pred p;\nelect.sync _|p, 0xffffffff;\nselp.u32 %0, 1, 0, p;\n}\n" : "=r"(p));
  return p;
}
__device__ __forceinline__ uint4 ld_nc4(const void* p) {
  uint4 v;
  asm volatile("ld.global.nc.L1::no_allocate.v4.u32 {%0,%1,%2,%3}, [%4];" : "=r"(v.x), "=r"(v.y), "=r"(v.z), "=r"(v.w) : "l"(p));
  return v;
}
__device__ __forceinline__ void st_cg4(void* p, uint4 v) {
  asm volatile("st.global.cg.v4.u32 [%0], {%1,%2,%3,%4};" ::"l"(p), "r"(v.x), "r"(v.y), "r"(v.z), "r"(v.w) : "memory");
}
__device__ __forceinline__ uint32_t mapa(uint32_t a, uint32_t cta) { uint32_t r; asm("mapa.shared::cluster.u32 %0, %1, %2;" : "=r"(r) : "r"(a), "r"(cta)); return r; }
__device__ __forceinline__ void st_async(uint32_t a, uint32_t v, uint32_t bar) {
  asm volatile("st.async.weak.shared::cluster.mbarrier::complete_tx::bytes.b32 [%0], %1, [%2];" ::"r"(a), "r"(v), "r"(bar) : "memory");
}
__device__ __forceinline__ void st_async4(uint32_t a, uint32_t x, uint32_t y, uint32_t z, uint32_t w, uint32_t bar) {
  asm volatile("st.async.weak.shared::cluster.mbarrier::complete_tx::bytes.v4.b32 [%0], {%1,%2,%3,%4}, [%5];" ::"r"(a), "r"(x), "r"(y), "r"(z), "r"(w), "r"(bar) : "memory");
}
__device__ __forceinline__ void tma3d_st(const CUtensorMap* m, uint32_t src, int c0, int c1, int c2) {
  asm volatile("cp.async.bulk.tensor.3d.global.shared::cta.bulk_group [%0, {%2, %3, %4}], [%1];" ::"l"(m), "r"(src), "r"(c0), "r"(c1), "r"(c2) : "memory");
}
__device__ __forceinline__ uint4 ld_rlx4(const void* p) {
  uint4 v;
  asm volatile("{\n.reg .b128 t;\n.reg .b64 a, b;\nld.relaxed.gpu.global.b128 t, [%4];\nmov.b128 {a, b}, t;\nmov.b64 {%0, %1}, a;\nmov.b64 {%2, %3}, b;\n}\n"
               : "=r"(v.x), "=r"(v.y), "=r"(v.z), "=r"(v.w) : "l"(p) : "memory");
  return v;
}
__device__ __forceinline__ void ld_stale4(uint4& v, const void* p, uint32_t tag) {
  asm volatile("{\n.reg .b128 t;\n.reg .b64 a, b;\n.reg .b32 x;\n.reg .pred p;\n"
               "lop3.b32 x, %0, %5, 1, 0x28;\nsetp.ne.u32 p, x, 0;\n"
               "mov.b64 a, {%0, %1};\nmov.b64 b, {%2, %3};\nmov.b128 t, {a, b};\n"
               "@p ld.relaxed.gpu.global.b128 t, [%4];\n"
               "mov.b128 {a, b}, t;\nmov.b64 {%0, %1}, a;\nmov.b64 {%2, %3}, b;\n}\n"
               : "+r"(v.x), "+r"(v.y), "+r"(v.z), "+r"(v.w) : "l"(p), "r"(tag) : "memory");
}
__device__ __forceinline__ void st_tag4(void* p, float a, float b, float c, float d, uint32_t tag) {
  asm volatile("{\n.reg .b128 t;\n.reg .b64 a, b;\nmov.b64 a, {%1, %2};\nmov.b64 b, {%3, %4};\nmov.b128 t, {a, b};\nst.relaxed.gpu.global.b128 [%0], t;\n}\n"
               ::"l"(p), "r"((__float_as_uint(a) & ~1u) | tag), "f"(b), "f"(c), "f"(d) : "memory");
}
__device__ __forceinline__ uint32_t stale8(const uint4 (&f)[8], uint32_t tag) {
  uint32_t r[4];
#pragma unroll
  for (int i = 0; i < 4; i++) asm("lop3.b32 %0, %1, %2, %3, 0x7E;" : "=r"(r[i]) : "r"(f[2 * i].x), "r"(f[2 * i + 1].x), "r"(tag));
  asm("lop3.b32 %0, %0, %1, %2, 0xFE;" : "+r"(r[0]) : "r"(r[1]), "r"(r[2]));
  return r[0] | r[3];
}

struct ConvC { uint32_t a1[2][4], wa[2], wb[2], sg; };
__device__ __forceinline__ uint64_t dsc(uint32_t lo, uint32_t hi) { return ((uint64_t)hi << 32) | lo; }
__device__ __forceinline__ uint32_t hfma(uint32_t a, uint32_t b, uint32_t c) { uint32_t r; asm("fma.rn.f16x2 %0, %1, %2, %3;" : "=r"(r) : "r"(a), "r"(b), "r"(c)); return r; }
__device__ __forceinline__ uint32_t hfnma(uint32_t a, uint32_t b, uint32_t c) { uint32_t r; asm("{.reg .b32 n; neg.f16x2 n, %1; fma.rn.f16x2 %0, n, %2, %3;}" : "=r"(r) : "r"(a), "r"(b), "r"(c)); return r; }
__device__ __forceinline__ uint32_t hmul16(uint32_t a, uint32_t b) { uint32_t r; asm("mul.rn.f16x2 %0, %1, %2;" : "=r"(r) : "r"(a), "r"(b)); return r; }
template <int N> __device__ __forceinline__ void keepu(uint32_t (&d)[N]) {
#pragma unroll
  for (int i = 0; i < N; i++) asm volatile("" : "+r"(d[i])::"memory");
}
__device__ __forceinline__ void conv_m1(const ConvC& K, uint32_t (&u)[16], uint32_t l) {
  wg_fence();
  wgmma_hrs_n64<1>(u, K.a1[0][0], K.a1[0][1], K.a1[0][2], K.a1[0][3], dsc(l, 32), 0);
  wgmma_hrs_n64<1>(u, K.a1[1][0], K.a1[1][1], K.a1[1][2], K.a1[1][3], dsc(l + 16, 32), 1);
  wg_commit();
}
__device__ __forceinline__ void conv_s2(const ConvC& K, uint32_t (&u)[16], uint32_t (&Z)[2][8], uint32_t dfl) {
  uint32_t fr[8], fi[8];
#pragma unroll
  for (int c = 0; c < 8; c++) {
    const uint32_t r = hfma(K.wa[c & 1], u[2 * c + 1], u[2 * c]);
    fi[c] = hfma(K.wb[c & 1], r, u[2 * c + 1]);
    fr[c] = hfma(K.wa[c & 1], fi[c], r);
  }
  wg_fence();
#pragma unroll
  for (int p = 0; p < 2; p++) {
    wgmma_hrs_n32<0>(Z[p], fr[4 * p], fr[4 * p + 2], fr[4 * p + 1], fr[4 * p + 3], dsc(dfl, 32), 0);
    wgmma_hrs_n32<0>(Z[p], fi[4 * p], fi[4 * p + 2], fi[4 * p + 1], fi[4 * p + 3], dsc(dfl + 16, 32), 1);
  }
  wg_commit();
}
__device__ __forceinline__ void conv_win(const ConvC& K, const uint32_t (&X)[2][8], uint32_t (&W)[2][8]) {
#pragma unroll
  for (int b = 0; b < 4; b++)
#pragma unroll
    for (int c = 0; c < 2; c++) {
      const uint32_t xr = X[b >> 1][2 * c + (b & 1)], xi = X[b >> 1][4 + 2 * c + (b & 1)];
      const int a = b ? b - 1 : 0;
      W[b >> 1][2 * c + (b & 1)] = b ? hfnma(K.sg, X[a >> 1][4 + 2 * c + (a & 1)], xr) : hmul16(xr, 0x3C003C00u);
      W[b >> 1][4 + 2 * c + (b & 1)] = b ? hfma(K.sg, X[a >> 1][2 * c + (a & 1)], xi) : hmul16(xi, 0x3C003C00u);
    }
}
template <int p>
__device__ __forceinline__ void conv_pw(uint32_t (&X)[2][8], uint32_t (&H)[2][8], uint32_t (&V)[8], uint32_t dil) {
  uint32_t pr[2][2], pi[2][2];
#pragma unroll
  for (int jj = 0; jj < 2; jj++)
#pragma unroll
    for (int c = 0; c < 2; c++) {
      const int j = 2 * p + jj;
      uint32_t sr = 0, si = 0;
#pragma unroll
      for (int a = 0; a <= j; a++) {
        const int b = j - a;
        const uint32_t hr = H[a >> 1][2 * c + (a & 1)], hi = H[a >> 1][4 + 2 * c + (a & 1)];
        const uint32_t xr = X[b >> 1][2 * c + (b & 1)], xi = X[b >> 1][4 + 2 * c + (b & 1)];
        sr = a == 0 ? hmul16(hr, xr) : hfma(hr, xr, sr);
        si = a == 0 ? hmul16(hr, xi) : hfma(hr, xi, si);
        sr = hfnma(hi, xi, sr);
        si = hfma(hi, xr, si);
      }
      pr[jj][c] = sr; pi[jj][c] = si;
    }
  wg_fence();
  wgmma_hrs_n32<0>(V, pr[0][0], pr[1][0], pr[0][1], pr[1][1], dsc(dil, 32), 0);
  wgmma_hrs_n32<0>(V, pi[0][0], pi[1][0], pi[0][1], pi[1][1], dsc(dil + 16, 32), 1);
  wg_commit();
}
template <int p>
__device__ __forceinline__ void conv_it(const ConvC& K, uint32_t (&V)[8], uint32_t vst) {
#pragma unroll
  for (int jj = 0; jj < 2; jj++) {
    uint32_t wr[2], wi[2];
#pragma unroll
    for (int c = 0; c < 2; c++) {
      const uint32_t r = hfnma(K.wa[c], V[4 + 2 * c + jj], V[2 * c + jj]);
      wi[c] = hfnma(K.wb[c], r, V[4 + 2 * c + jj]);
      wr[c] = hfnma(K.wa[c], wi[c], r);
    }
    stsm4(vst + (2 * p + jj) * 2048, wr[0], wr[1], wi[0], wi[1]);
  }
}
__device__ __forceinline__ void conv_m4(uint32_t (&y)[8], uint32_t (&a)[4][4], uint32_t d4l) {
  wg_fence();
  wgmma_hrs_n32<0>(y, a[0][0], a[0][1], a[0][2], a[0][3], dsc(d4l, 64), 0);
#pragma unroll
  for (int s = 1; s < 4; s++) wgmma_hrs_n32<0>(y, a[s][0], a[s][1], a[s][2], a[s][3], dsc(d4l + s * 16, 64), 1);
  wg_commit();
}

struct Params {
  CUtensorMap tmX, tmW, tmWo, tmWo1, tmK, tmV, tmQ, tmOA, tmOB;
  const __nv_bfloat16 *shift_k, *h, *D, *x, *w, *wo, *q, *k, *v;
  float *part, *kv;
  uint4 *o, *h16;
  unsigned *ocnt, *epoch;
  const uint32_t *thr, *img;
};

__global__ void __cluster_dims__(2, 1, 1) __launch_bounds__(384, 1) fused_kernel(const __grid_constant__ Params P) {
  extern __shared__ __align__(1024) uint8_t smem[];
  const uint32_t sb = smem_u32(smem);
  const uint32_t bars = sb + OFF_BAR;
  const int tid = threadIdx.x, lane = tid & 31;
  const int warp = __shfl_sync(~0u, tid >> 5, 0);
  const int rank = blockIdx.x & 1, cl = blockIdx.x >> 1;
  const int mb = cl < 4 ? 4 + cl : cl < 36 ? (cl - 4) >> 3 : 4 + (cl - 36) / 7;
  const int hb = (cl - 36) % 7;
  const int hq = cl < 4 ? A0COL : cl < 36 ? (cl - 4) & 7 : hb + (hb >= A0COL);
  const int hp = 2 * hq + rank;
  const int rb = 2 * mb + (hq >> 2), cb = hq & 3;
#define BAR(i) (bars + 8 * (i))

  if (tid == 0) { STAMP(0, 0); GSTAMP(0, 30); }
  if (warp == 8) {
    if (elect_one()) {
      mbar_init(BAR(B_FULL1), 1);
      asm volatile("fence.mbarrier_init.release.cluster;" ::: "memory");
      mbar_expect(BAR(B_FULL1), STAGE_BYTES);
      tma3d(sb + 32768, &P.tmW, hp * 64, 0, 0, BAR(B_FULL1));
    }
    if (lane == 0) STAMP(3, 21);
  } else if (lane == 0) {
    const int wi = warp - (warp > 8);
#pragma unroll
    for (int r = 0; r < 6; r++)
      if (r < 5 || wi < B_COUNT - 56) mbar_init(BAR(1 + 11 * r + wi), ((uint32_t)(bar_counts(r) >> (4 * wi)) & 15) + 1);
    asm volatile("fence.mbarrier_init.release.cluster;" ::: "memory");
  }
  if (tid == 0) STAMP(2, 6);
  asm volatile("barrier.cluster.arrive.relaxed.aligned;\nbarrier.cluster.wait.aligned;" ::: "memory");
  if (warp == 8 && elect_one()) tma2d_mc(sb + rank * 16384, &P.tmX, 0, mb * 256 + rank * 128, BAR(B_FULL1));
  if (tid == 256) STAMP(2, 7);

  if (warp < 8) {
    asm volatile("setmaxnreg.inc.sync.aligned.u32 224;");
    const int wg = warp >> 2, w = warp & 3, g = lane >> 2, q = lane & 3, t = tid & 127;
    const bool elect = (t == 0);
    const uint32_t s16 = (sb & 0x3FFFF) >> 4;
    constexpr uint32_t SW128 = 64 | (1u << 30);
    uint32_t pq[2][16];
    ConvC K;
    {
      float acc[2][96];
      int st = 0, ph = 0;
#pragma unroll 1
      for (int kb = 0; kb < 14; kb++) {
        mbar_wait(BAR(B_FULL1 + st), ph);
        if (kb == 0 && elect) { STAMP(wg, 1); GSTAMP(wg, 26); }
        if (kb == 8 && elect) { STAMP(wg, 16); GSTAMP(wg, 25); }
        if (tid == 0) STAMP(2, 8 + kb);
        const uint32_t da = s16 + st * (STAGE_BYTES >> 4) + wg * 1024 + (1 << 16);
        const uint32_t db = s16 + st * (STAGE_BYTES >> 4) + 2048 + (512 << 16);
        wg_fence();
#pragma unroll
        for (int ks = 0; ks < 4; ks++) {
          wgmma_ss_n192<0, 1>(acc[0], dsc(da + ks * 2, SW128), dsc(db + ks * 128, SW128), (kb | ks) != 0);
          wgmma_ss_n192<0, 1>(acc[1], dsc(da + 512 + ks * 2, SW128), dsc(db + ks * 128, SW128), (kb | ks) != 0);
        }
        wg_commit();
        wg_wait<1>();
        if (kb > 0 && t < 2) mbar_arrive_cl(BAR(B_EMPTY1 + (st == 0 ? 2 : st - 1)), t);
        if (++st == 3) { st = 0; ph ^= 1; }
      }
#define TAIL_MMA(mt, stage) do { wg_fence(); _Pragma("unroll") for (int ks = 0; ks < 4; ks++) \
        wgmma_ss_n192<0, 1>(acc[mt], dsc(s16 + (stage) * (STAGE_BYTES >> 4) + wg * 1024 + (mt) * 512 + (1 << 16) + ks * 2, SW128), \
                            dsc(s16 + (stage) * (STAGE_BYTES >> 4) + 2048 + (512 << 16) + ks * 128, SW128), 1); wg_commit(); } while (0)
      mbar_wait(BAR(B_FULL1 + 2), 0);
      TAIL_MMA(0, 2);
      wg_wait<1>();
      if (t < 2) mbar_arrive_cl(BAR(B_EMPTY1 + 1), t);
      mbar_wait(BAR(B_FULL1 + 0), 1);
      TAIL_MMA(0, 0);
      TAIL_MMA(1, 2);
      if (!TSPLIT) TAIL_MMA(1, 0);
      const uint32_t lrow = sb + (16 * w + 8 * ((lane >> 3) & 1) + (lane & 7)) * 128 + (((lane >> 4) ^ (lane & 7)) << 4);
      const uint32_t pko = OFF_PK + wg * 8192, vo0 = 6 * 16384 + wg * 8192, vo1 = 7 * 16384 + wg * 16384;
#define E1K(mt, i) do { if (opaque_true()) { _Pragma("unroll") for (int j = (i); j < (i) + 2; j++) { \
          const float* a = &acc[mt][32 + 8 * j]; const float* b = a + 32; const uint32_t o = lrow ^ (j * 32); \
          stsm4(o + ((mt) ? vo1 : vo0), pk2(b[0], b[1]), pk2(b[2], b[3]), pk2(b[4], b[5]), pk2(b[6], b[7])); \
          stsm4(o + pko + (mt) * 16384, phi2(a[0], a[1]), phi2(a[2], a[3]), phi2(a[4], a[5]), phi2(a[6], a[7])); } } } while (0)
#define E1Q(mt) do { if (opaque_true()) { _Pragma("unroll") for (int i = 0; i < 16; i++) pq[mt][i] = phi2(acc[mt][2 * i], acc[mt][2 * i + 1]); } } while (0)
      mbar_wait(BAR(B_EMPTY1 + 1), 0);
      if (TSPLIT) wg_wait<1>(); else wg_wait<2>();
      keep(acc[0]);
      if (elect) STAMP(wg, 18);
      E1K(0, 0);
      if (TSPLIT) TAIL_MMA(1, 0);
      E1K(0, 2);
      if (elect) STAMP(wg, 19);
      if (QPOS == 0) E1Q(0);
      if (elect) STAMP(wg, 20);
      {
        const uint4* ct = (const uint4*)P.thr + t;
#pragma unroll
        for (int s = 0; s < 2; s++) { const uint4 u = ld_nc4(ct + s * 128); K.a1[s][0] = u.x; K.a1[s][1] = u.y; K.a1[s][2] = u.z; K.a1[s][3] = u.w; }
        const uint4 u = ld_nc4(ct + 2 * 128);
        K.wa[0] = u.x; K.wa[1] = u.y; K.wb[0] = u.z; K.wb[1] = u.w;
        K.sg = (lane & 4) ? 0xBC00BC00u : 0x3C003C00u;
      }
      mbar_wait(BAR(B_XT), 0);
      const uint32_t tag = ~*(volatile unsigned*)(smem + OFF_EPOCH) & 1;
      wg_wait<0>();
      keep(acc[1]);
      if (t < 2) mbar_arrive_cl(BAR(B_EMPTY1 + 0), t);
      if (elect) { STAMP(wg, 2); GSTAMP(wg, 27); }
      E1K(1, 0);
      E1K(1, 2);
      fence_async();
      bar_sync(1 + wg);
      if (elect) STAMP(wg, 3);
      float kva[36];
      wg_fence();
#pragma unroll
      for (int ks = 0; ks < 8; ks++) {
        const uint32_t vb = ((ks >> 2 ? vo1 : vo0) >> 4) + (ks & 3) * 128;
        wgmma_ss_n72<1, 1>(kva, dsc(s16 + (pko >> 4) + (ks >> 2) * 1024 + (ks & 3) * 128 + (1 << 16), SW128),
                           dsc(s16 + vb + (((OFF_ONES >> 4) - vb) << 16), SW128), ks != 0);
      }
      wg_commit();
      if (QPOS == 1) E1Q(0);
      wg_wait<0>();
      keep(kva);
      if (elect) STAMP(wg, 24);
      {
        float4 p[5];
#pragma unroll
        for (int c = 0; c < 4; c++)
          p[c] = w < 2 ? make_float4(kva[4 * c], kva[4 * c + 1], kva[4 * c + 2], kva[4 * c + 3])
                       : make_float4(kva[16 + 4 * c], kva[17 + 4 * c], kva[18 + 4 * c], kva[19 + 4 * c]);
        p[4] = make_float4(kva[32], kva[34], __shfl_down_sync(~0u, kva[32], 4), __shfl_down_sync(~0u, kva[34], 4));
        float4* hand = (float4*)(smem + 8 * 16384 + 8192 - (w >> 1) * 16384) + (t & 63);
        if ((w >> 1) != wg) {
#pragma unroll
          for (int c = 0; c < 5; c++) hand[c * 64] = p[c];
          asm volatile("bar.arrive %0, 128;" ::"r"(5 + (w >> 1)) : "memory");
        } else {
          float* dst = P.part + (hp * 8 + mb) * 2176;
          asm volatile("bar.sync %0, 128;" ::"r"(5 + (w >> 1)) : "memory");
#pragma unroll
          for (int c = 0; c < 5; c++) { const float4 u = hand[c * 64]; p[c].x += u.x; p[c].y += u.y; p[c].z += u.z; p[c].w += u.w; }
#pragma unroll
          for (int c = 0; c < 5; c++)
            if (c < 4 || !(lane & 7)) st_tag4(c < 4 ? dst + (c * 128 + t) * 4 : dst + 2048 + 16 * w + 2 * g, p[c].x, p[c].y, p[c].z, p[c].w, tag);
        }
        __syncwarp();
        if (lane == 0) mbar_arrive(BAR(B_PKFREE));
      }
      if (elect) STAMP(wg, 4);
      if (QPOS == 2) E1Q(0);
      E1Q(1);
    }
    mbar_wait(BAR(B_H), 0);
    if (elect) STAMP(wg, 5);
    {
      const uint32_t dfl = s16 + (OFF_F2F >> 4) + (8 << 16), dil = s16 + (OFF_F2I >> 4) + (8 << 16), d4l = s16 + (OFF_F4 >> 4) + (8 << 16);
      const uint32_t xl = s16 + (OFF_XT >> 4) + 4 * wg * (XT_STRIDE >> 4) + (8 << 16);
      const uint32_t hl = s16 + (OFF_H >> 4) + wg * 512 + (8 << 16);
      uint32_t vst = sb + wg * 8192 + w * 512 + lane * 16, vld = sb + wg * 8192 + w * 2048 + lane * 16;
      uint32_t ya = mapa(sb + OFF_XT + 4 * wg * XT_STRIDE + (2 * rank + (w & 1)) * 1024 + lane * 16, w >> 1);
      const uint32_t ybar = mapa(BAR(B_Y), w >> 1);
      asm volatile("" : "+r"(vst), "+r"(vld), "+r"(ya));
      uint32_t ux[16], uh[16], W[2][8], V0[8], V1[8], y[8], a[4][4];
      uint4* const ot = P.o + ((2 * mb + wg) * 16 + hq) * 1024 + (16 * w + g) * 8 + ((4 * rank + q) ^ g);
#define YOUT(i) do { if ((w >> 1) == rank) { \
          asm volatile("st.shared.v4.b32 [%0], {%1,%2,%3,%4};" ::"r"(ya + (i) * XT_STRIDE), "r"(y[0]), "r"(y[2]), "r"(y[4]), "r"(y[6]) : "memory"); \
          asm volatile("st.shared.v4.b32 [%0], {%1,%2,%3,%4};" ::"r"(ya + (i) * XT_STRIDE + 512), "r"(y[1]), "r"(y[3]), "r"(y[5]), "r"(y[7]) : "memory"); \
        } else { \
          mbar_wait(BAR(B_XFREE + 4 * wg + (i)), 0); \
          st_async4(ya + (i) * XT_STRIDE, y[0], y[2], y[4], y[6], ybar); \
          st_async4(ya + (i) * XT_STRIDE + 512, y[1], y[3], y[5], y[7], ybar); } } while (0)
      auto ocalc = [&](const int hh) {
        if (hh == 0) {
          if (elect) STAMP(wg, 8);
          mbar_wait(BAR(B_KV), 0);
          if (elect) STAMP(wg, 9);
        }
        float oa[2][20];
        wg_fence();
#pragma unroll
        for (int m = 0; m < 4; m++) {
          const uint32_t* p = &pq[m & 1][8 * hh + 4 * (m >> 1)];
          wgmma_rs_n40<1>(oa[m & 1], p[0], p[1], p[2], p[3], dsc(s16 + (OFF_KVB >> 4) + hh * 160 + (m >> 1) * 16 + (8 << 16), 32), m >> 1);
        }
        wg_commit();
        wg_wait<0>();
#pragma unroll
        for (int mt = 0; mt < 2; mt++) {
          float (&o)[20] = oa[mt];
          keep(o);
          const uint32_t den = hadd(pk2(o[16], o[18]), 0x35863586u);
#pragma unroll
          for (int r = 0; r < 2; r++) {
            const float ri = rcp_fast(__uint_as_float(r ? (den & 0xFFFF0000u) : (den << 16)));
            uint4 u;
            u.x = pk2(o[2 * r] * ri, o[2 * r + 1] * ri);
            u.y = pk2(o[4 + 2 * r] * ri, o[5 + 2 * r] * ri);
            u.z = pk2(o[8 + 2 * r] * ri, o[9 + 2 * r] * ri);
            u.w = pk2(o[12 + 2 * r] * ri, o[13 + 2 * r] * ri);
            st_cg4(ot + hh * 8 * 1024 + (64 * mt + 8 * r) * 8, u);
          }
        }
        __syncwarp();
        if (lane == 0) mbar_arrive(BAR(hh ? B_ODONE1 : B_ODONE));
        if (hh == 0 && elect) STAMP(wg, 10);
      };
      uint32_t X[4][2][8], H[4][2][8];
      conv_m1(K, ux, xl);
      conv_m1(K, uh, hl);
      wg_wait<1>(); keepu(ux);
      if (lane == 0) mbar_arrive_cl(BAR(B_XFREE + 4 * wg), rank ^ 1);
      conv_s2(K, ux, X[0], dfl);
      wg_wait<1>(); keepu(uh);
      conv_s2(K, uh, H[0], dfl);
#pragma unroll
      for (int i = 0; i < 4; i++) {
        const bool nx = i < 3;
        const int n = nx ? i + 1 : i;
        const uint32_t vo = (i & 1) ? OFF_H + (i >> 1) * 16384 : OFF_VP;
        if (2 * i == OCH) ocalc(0);
        if (2 * i == OCH + O1D) ocalc(1);
        if (nx) {
          conv_m1(K, ux, xl + n * (XT_STRIDE >> 4));
          conv_m1(K, uh, hl + (n >> 1) * 1024 + (n & 1) * 256);
        }
        if (2 * i != OCH && 2 * i != OCH + O1D) { if (nx) { if (i > 0) wg_wait<3>(); else wg_wait<2>(); } else wg_wait<1>(); }
        keepu(X[i][0]); keepu(X[i][1]); keepu(H[i][0]); keepu(H[i][1]);
        conv_win(K, X[i], W);
        conv_pw<0>(W, H[i], V0, dil);
        conv_pw<1>(W, H[i], V1, dil);
        wg_wait<2>();
        if (i > 0) { keepu(y); YOUT(i - 1); }
        if (2 * i + 1 == OCH) ocalc(0);
        if (2 * i + 1 == OCH + O1D) ocalc(1);
        if (nx) {
          keepu(ux); keepu(uh);
          if (lane == 0) mbar_arrive_cl(BAR(B_XFREE + 4 * wg + n), rank ^ 1);
          conv_s2(K, ux, X[n], dfl);
          wg_wait<1>();
        } else wg_wait<0>();
        keepu(V0); keepu(V1);
        conv_it<0>(K, V0, vst + vo);
        conv_it<1>(K, V1, vst + vo);
        bar_sync(1 + wg);
#pragma unroll
        for (int s = 0; s < 4; s++) ldsm4t(a[s], vld + vo + s * 512);
        if (nx) conv_s2(K, uh, H[n], dfl);
        conv_m4(y, a, d4l);
        if (i > 0 && lane < 2) mbar_arrive_cl(BAR(B_AFREE + i - 1), lane);
        if (elect && i < 3) STAMP(wg, i < 2 ? 6 + i : 9 + i);
      }
      wg_wait<0>(); keepu(y);
      YOUT(3);
      __syncwarp();
      if (lane == 0) mbar_arrive(BAR(B_Y));
      if (elect) STAMP(wg, 12);
    }
    {
      float acc[64];
#pragma unroll 1
      for (int kb = 0; kb < 16; kb++) {
        mbar_wait(BAR(B_FULL2 + kb), 0);
        if (kb == 0 && elect) { STAMP(wg, 13); GSTAMP(wg, 28); }
        const uint32_t da = s16 + ((uint32_t)(SLOT_A >> (4 * kb)) & 15) * 1024 + wg * 512 + (1 << 16);
        const uint32_t db = s16 + ((uint32_t)(SLOT_B >> (4 * kb)) & 15) * 1024 + (512 << 16);
        if (kb == HOLD2 && wg == 0) asm volatile("bar.sync 3, 256;" ::: "memory");
        wg_fence();
#pragma unroll
        for (int ks = 0; ks < 4; ks++) wgmma_ss_n128<0, 1>(acc, dsc(da + ks * 2, SW128), dsc(db + ks * 128, SW128), (kb | ks) != 0);
        wg_commit();
        if (HOLD2 < 16 && kb == 15 && wg == 1) asm volatile("bar.arrive 3, 256;" ::: "memory");
        wg_wait<1>();
        if (kb > 0 && kb < 13 && t < 2 && (kb <= 11 || t == rank)) mbar_arrive_cl(BAR(B_CONS2 + kb - 1), t);
      }
      wg_wait<0>();
      keep(acc);
      if (elect) { STAMP(wg, 14); GSTAMP(wg, 29); }
      mbar_wait(BAR(B_CONS2 + 11), 0);
      const uint32_t stg = sb + ((uint32_t)((wg ? SLOT_A : SLOT_B) >> 44) & 15) * 16384;
      const uint32_t lrow = stg + (16 * w + 8 * ((lane >> 3) & 1) + (lane & 7)) * 128 + (((lane >> 4) ^ (lane & 7)) << 4);
#pragma unroll
      for (int cp = 0; cp < 8; cp++) {
        const float* a = &acc[8 * cp];
        stsm4((lrow ^ ((cp & 3) * 32)) + (cp >> 2) * 8192, pk2(a[0], a[1]), pk2(a[2], a[3]), pk2(a[4], a[5]), pk2(a[6], a[7]));
      }
      fence_async();
      bar_sync(1 + wg);
      if (elect) {
        const int col = 1024 + 256 * cb + 128 * rank, row = 128 * rb + 64 * wg;
        tma2d_st(&P.tmOB, stg, col, row);
        tma2d_st(&P.tmOB, stg + 8192, col + 64, row);
        asm volatile("cp.async.bulk.commit_group;\ncp.async.bulk.wait_group.read 0;" ::: "memory");
        STAMP(wg, 15); GSTAMP(wg, 31); PDUMP(wg);
      }
    }
  } else {
    asm volatile("setmaxnreg.dec.sync.aligned.u32 56;");
    if (warp == 8) {
      if (lane == 0) STAMP(3, 20);
      int st = 1, ph = 1;
      const uint8_t* pfx = (const uint8_t*)P.x + (mb * 256 + hp * 16 + (lane & 15)) * 2048;
      const uint8_t* pfw = (const uint8_t*)P.w + (mb * 8 + (lane & 7)) * 6144 + (lane >> 3) * 2048 + hp * 128;
#pragma unroll 1
      for (int kb = 1; kb < 16; kb++) {
        if (kb >= 3) mbar_wait(BAR(B_EMPTY1 + st), ph);
        const uint32_t sa = sb + st * STAGE_BYTES;
        if (elect_one()) {
          mbar_expect(BAR(B_FULL1 + st), STAGE_BYTES);
          tma2d_mc(sa + rank * 16384, &P.tmX, kb * 64, mb * 256 + rank * 128, BAR(B_FULL1 + st));
          tma3d(sa + 32768, &P.tmW, hp * 64, kb * 64, 0, BAR(B_FULL1 + st));
        }
        if (kb == 1 && lane == 0) STAMP(2, 24);
        if (PFD && kb >= 2) {
#pragma unroll 1
          for (int j = kb == 2 ? 3 : kb + PFD; j <= kb + PFD && j < 16; j++) {
            if (lane < 16) asm volatile("prefetch.global.L2 [%0];" ::"l"(pfx + j * 128));
            if (lane < 24) asm volatile("prefetch.global.L2 [%0];" ::"l"(pfw + j * (64 * 6144)));
          }
          if (kb >= QPF && kb < QPF + 8) asm volatile("prefetch.global.L2 [%0];" ::"l"((const uint8_t*)P.q + (blockIdx.x * 256 + (kb - QPF) * 32 + lane) * 128));
          if (kb >= 12) asm volatile("prefetch.global.L2 [%0];" ::"l"((const uint8_t*)P.wo + (blockIdx.x * 128 + (kb - 12) * 32 + lane) * 128));
        }
        if (++st == 3) { st = 0; ph ^= 1; }
      }
      if (lane == 0) STAMP(2, 1);
      const unsigned epoch = P.epoch[blockIdx.x];
#define SLOT(tab, kb) (sb + ((uint32_t)((tab) >> (4 * (kb))) & 15) * 16384)
#define LOAD_B(kb) tma4d(SLOT(SLOT_B, kb), &P.tmWo, 0, ((kb) >> 3) * 32, 2 * ((kb) & 7), 4 * cb + 2 * rank, BAR(B_FULL2 + (kb)))
#define LOAD_A(kb) bulk_ld_mc(SLOT(SLOT_A, kb) + rank * 8192, P.o + (rb * 16 + (kb)) * 1024 + rank * 512, 8192, BAR(B_FULL2 + (kb)))
      mbar_wait(BAR(B_EMPTY1 + 0), 1);
      mbar_wait(BAR(B_XT), 0);
      if (elect_one()) { mbar_expect(BAR(B_H), 32768); bulk_ld(sb + OFF_H, P.h16 + blockIdx.x * 2048, 32768, BAR(B_H)); }
      {
        const uint32_t c0 = clock();
#pragma unroll 1
        for (int i = 0; i < 14; i++) {
          const int kb = i >> 1;
          if (i == 4) mbar_wait(BAR(B_PKFREE), 0);
          while (__any_sync(~0u, (uint32_t)clock() - c0 < BSTART + i * BPACE)) __nanosleep(32);
          if (elect_one()) {
            if (!(i & 1)) mbar_expect(BAR(B_FULL2 + kb), 16384);
            tma4d(SLOT(SLOT_B, kb) + (i & 1) * 8192, &P.tmWo1, 0, 0, 2 * kb, 4 * cb + 2 * rank + (i & 1), BAR(B_FULL2 + kb));
            if (i == 0) mbar_expect(BAR(B_Q), 8192);
            if (i < 4) tma3d(sb + OFF_SPARE + 2048 * i, &P.tmQ, 16 * cl, 64 * rank + 32 * (i >> 1), 2 * ((i + 6) & 7), BAR(B_Q));
          }
        }
      }
      if (lane == 0) STAMP(2, 2);
      mbar_wait(BAR(B_AFREE), 0);
      if (elect_one()) mbar_expect(BAR(B_FULL2), 16384);
      {
        const uint32_t dst = SLOT(SLOT_A, 0) + rank * 8192;
        const uint4* src = P.o + rb * 16 * 1024 + rank * 512;
        poll_ge(&P.ocnt[rb * 32], 16 * (epoch + 1));
        asm volatile("fence.proxy.async.global;" ::: "memory");
        if (lane == 0) STAMP(2, 3);
        if (elect_one()) bulk_ld_mc(dst, src, 8192, BAR(B_FULL2));
        if (lane == 0) STAMP(3, 23);
      }
#pragma unroll 1
      for (int kb = 1; kb < 7; kb++) {
        mbar_wait(BAR(kb < 3 ? B_AFREE + kb : B_CONS2 + ((kb - 3) >> 1)), 0);
        if (elect_one()) { mbar_expect(BAR(B_FULL2 + kb), 16384); LOAD_A(kb); }
      }
#pragma unroll 1
      for (int kb = 7; kb < 16; kb++) {
        mbar_wait(BAR(B_CONS2 + kb - 5), 0);
        if (kb == 8) mbar_wait(BAR(B_O1RDY), 0);
        if (elect_one()) { mbar_expect(BAR(B_FULL2 + kb), 32768); LOAD_A(kb); LOAD_B(kb); }
      }
      if (lane == 0) { P.epoch[blockIdx.x] = epoch + 1; STAMP(2, 5); PDUMP(2); }
    } else {
      const uint32_t clk0 = __shfl_sync(~0u, (uint32_t)clock(), 0);
      const int hw = warp - 9, g = lane >> 2, q = lane & 3;
      const unsigned epoch = __shfl_sync(~0u, P.epoch[blockIdx.x], 0);
      const uint32_t tag = ~epoch & 1;
      const uint32_t sbar = BAR(B_STG + 2 * hw);
      int ph = 0;
      {
#define KV_PREFETCH(c, ln) do { const int off_ = (1024 * (blockIdx.x >> 6) + 128 * (c) + 2 * (blockIdx.x & 63)) * 2048 + (ln) * 128; \
          asm volatile("prefetch.global.L2 [%0];" ::"l"((const uint8_t*)P.k + off_)); asm volatile("prefetch.global.L2 [%0];" ::"l"((const uint8_t*)P.v + off_)); } while (0)
        *(uint32_t*)(smem + OFF_TAP + 4 * lane) = __ldg((const uint32_t*)(P.shift_k + 64 * cl) + lane);
        *(float*)(smem + OFF_D + 4 * (lane & 7)) = __bfloat162float(P.D[blockIdx.x * 8 + (lane & 7)]);
        __syncwarp();
        if (hw == 1) asm volatile("prefetch.global.L2 [%0];" ::"l"(P.thr + (lane + 32 * (blockIdx.x & 1)) * 32));
        if (hw == 0 && elect_one()) {
          *(volatile unsigned*)(smem + OFF_EPOCH) = epoch;
          mbar_expect(BAR(B_XRAW), 16384);
          mbar_expect(BAR(B_Y), 16384 + 64);
        }
#pragma unroll 1
        for (int i = tid - 288; i < 594; i += 96)
          st_tag4(i < 528 ? P.part + (hp * 8 + mb) * 2176 + 4 * i : P.kv + hp * 2176 + 4 * (i < 592 ? 64 * mb + i - 528 : 512 + 2 * mb + i - 592), 0.f, 0.f, 0.f, 0.f, tag ^ 1);
        if (lane == 0) STAMP(3, hw);
        __syncwarp();
        uint32_t ehs = 0;
        const uint32_t kbuf = sb + OFF_F2F + hw * 8704;
#pragma unroll 1
        for (int n = 0; n < 6; n++) {
          const bool isH = n < 3;
          const int c = hw + 3 * (isH ? n : n - 3);
          if (n == 3) {
            if (lane == 0) STAMP(3, 3 + hw);
            asm volatile("fence.proxy.async;" ::: "memory");
            asm volatile("bar.sync 4, 96;" ::: "memory");
            if (hw == 0 && elect_one()) { mbar_expect(BAR(B_XT), 10240); bulk_ld(sb + OFF_F2F, P.img, 10240, BAR(B_XT)); }
            mbar_wait(BAR(B_XRAW), 0);
          }
          if (c >= 8) continue;
          if (isH) {
            while (__any_sync(~0u, (uint32_t)clock() - clk0 < HSTART + c * PACE)) __nanosleep(64);
            if (elect_one()) {
              mbar_expect(sbar, 4352 + 4096);
              tma4d(kbuf, &P.tmK, 16 * cl, 0, 128 * rank + 16 * c - 1, 0, sbar);
              tma4d(kbuf + 4352, &P.tmV, 16 * cl, 0, 128 * rank + 16 * c, 0, sbar);
            }
          }
          int ln;
          asm volatile("mov.u32 %0, %%laneid;" : "=r"(ln));
          {
            uint8_t* dst = (isH ? (uint8_t*)P.h16 + (blockIdx.x * 8 + (c & 2) * 2 + (c >> 2) * 2 + (c & 1)) * 4096 : smem + OFF_XT + c * XT_STRIDE)
                         + ((ln >> 4) * 512 + (ln & 15) * 16);
            const uint8_t* src0 = isH ? (const uint8_t*)P.h + (blockIdx.x * 8 + c) * 4096 + ((ln & 15) * 32 + (ln & 16)) : dst;
            const uint8_t* src1 = src0 + (isH ? 512 : 256);
            uint32_t v[32];
#pragma unroll
            for (int i = 0; i < 8; i++) {
              const uint4 u = *(const uint4*)(((i & 1) ? src1 : src0) + (i >> 1) * 1024);
              v[4 * i] = u.x; v[4 * i + 1] = u.y; v[4 * i + 2] = u.z; v[4 * i + 3] = u.w;
            }
            const int e = normalise(v, (isH && ln == 0) ? *(const float*)(smem + OFF_D + 4 * c) : 0.f);
#pragma unroll
            for (int i = 0; i < 8; i++)
              *(uint4*)(dst + (i >> 1) * 1024 + (i & 1) * 256) = make_uint4(v[4 * i], v[4 * i + 1], v[4 * i + 2], v[4 * i + 3]);
            if (lane == 0 && hw == 0 && n < 2) STAMP(3, 16 + 2 * n);
            if (!isH) {
              if (ln < 2) st_async(mapa(sb + OFF_SCALE + (8 * rank + c) * 4, ln), min(max(e + (int)(ehs & 255) - 124, 1), 254) << 23, mapa(BAR(B_Y), ln));
              ehs >>= 8;
              if (c < 6 && elect_one()) {
                if (c < 3) mbar_expect(sbar, 4096);
                tma3d(sb + OFF_STG + 2048 * c, &P.tmQ, 16 * cl, 64 * rank, 2 * c, sbar);
              }
              continue;
            }
            ehs |= e << (8 * n);
          }
          if (c < 5) asm volatile("prefetch.global.L2 [%0];" ::"l"((const uint8_t*)P.h + (blockIdx.x * 8 + c + 3) * 4096 + ln * 128));
          const int kr = (ln >> 3) * 34 + 2 + (ln & 7), hr = ((ln >> 3) | 2) * 34 + (ln & 7), vr = (ln >> 3) * 32 + (ln & 7);
          const uint32_t ka = kbuf + kr * 32 + ((kr & 4) << 2), ha = kbuf + hr * 32 + ((hr & 4) << 2), va = kbuf + 4352 + vr * 32 + ((vr & 4) << 2);
          const uint32_t xo = sb + OFF_XT + (ln >> 2) * XT_STRIDE + rank * 2048 + (ln & 1) * 512 + (ln & 2) * 8 + (c >> 2) * 1024 + (c & 3) * 128;
          const uint2 tap[2] = {*(const uint2*)(smem + OFF_TAP + (ln >> 2) * 8), *(const uint2*)(smem + OFF_TAP + 64 + (ln >> 2) * 8)};
          mbar_wait(sbar, ph);
          ph ^= 1;
#pragma unroll 1
          for (int grp = 0; grp < 4; grp++) {
            uint32_t vv[2][4], kk[2][6];
#pragma unroll
            for (int cg = 0; cg < 2; cg++) {
              uint32_t u[4];
              asm volatile("ldmatrix.sync.aligned.m8n8.x2.trans.shared.b16 {%0,%1}, [%2];" : "=r"(kk[cg][0]), "=r"(kk[cg][1]) : "r"((ha ^ (cg * 16)) + grp * 256) : "memory");
              ldsm4t(u, (ka ^ (cg * 16)) + grp * 256);
              kk[cg][2] = u[0]; kk[cg][3] = u[1]; kk[cg][4] = u[2]; kk[cg][5] = u[3];
              ldsm4t(vv[cg], (va ^ (cg * 16)) + grp * 256);
            }
            if (!opaque_true()) __trap();
#pragma unroll
            for (int cg = 0; cg < 2; cg++) {
              const uint32_t t0 = __byte_perm(tap[cg].x, 0, 0x1010), t1 = __byte_perm(tap[cg].x, 0, 0x3232);
              const uint32_t t2 = __byte_perm(tap[cg].y, 0, 0x1010), t3 = __byte_perm(tap[cg].y, 0, 0x3232);
              uint32_t od[5];
#pragma unroll
              for (int i = 0; i < 5; i++) od[i] = __byte_perm(kk[cg][i], kk[cg][i + 1], 0x5432);
#pragma unroll
              for (int m = 0; m < 4; m++)
                vv[cg][m] = hmul(hadd(hadd(hadd(hmul(od[m], t3), hmul(kk[cg][m + 1], t2)), hmul(od[m + 1], t1)), hmul(kk[cg][m + 2], t0)), vv[cg][m]);
              if (cg == rank) asm volatile("st.shared.v4.b32 [%0], {%1,%2,%3,%4};" ::"r"(xo + grp * 32), "r"(vv[cg][0]), "r"(vv[cg][1]), "r"(vv[cg][2]), "r"(vv[cg][3]) : "memory");
              else st_async4(mapa(xo + grp * 32, cg), vv[cg][0], vv[cg][1], vv[cg][2], vv[cg][3], mapa(BAR(B_XRAW), cg));
            }
          }
          if (lane == 0 && hw == 0 && n < 2) STAMP(3, 17 + 2 * n);
        }
      }
      fence_async();
      __syncwarp();
      if (lane == 0) { mbar_arrive(BAR(B_XT)); STAMP(3, 13 + hw); }
      mbar_wait(BAR(B_PKFREE), 0);
      if (hw == 0 && lane == 0) STAMP(3, 24);
      if (PD1) __nanosleep(PD1);
      {
        const int pi = hw < 2 ? 64 * mb - 288 + tid : 512 + 2 * mb + (lane & 1);
        const float* psrc = P.part + hp * 8 * 2176 + 4 * pi;
        uint4 f[8];
#pragma unroll
        for (int p = 0; p < 8; p++) f[p] = ld_rlx4(psrc + p * 2176);
        if (!opaque_true()) __trap();
#pragma unroll 1
        for (int n = 0; __any_sync(~0u, stale8(f, tag) & 1); n++) {
#pragma unroll
          for (int p = 0; p < 8; p++) ld_stale4(f[p], psrc + p * 2176, tag);
          if (n > SPIN_LIMIT) __trap();
        }
        float s0 = 0.f, s1 = 0.f, s2 = 0.f, s3 = 0.f;
#pragma unroll
        for (int p = 0; p < 8; p++) { s0 += __uint_as_float(f[p].x); s1 += __uint_as_float(f[p].y); s2 += __uint_as_float(f[p].z); s3 += __uint_as_float(f[p].w); }
        if (hw < 2 || lane < 2) st_tag4(P.kv + hp * 2176 + (4 * pi), s0, s1, s2, s3, tag);
      }
      if (lane == 0 && hw == 0) STAMP(3, 8);
      if (hw == 2) {
        unsigned* cnt = P.ocnt + (2 * mb + lane) * 32;
#pragma unroll 1
        for (int hh = 0; hh < 2; hh++) {
          mbar_wait(BAR(hh ? B_ODONE1 : B_ODONE), 0);
          if (lane < 2) asm volatile("red.release.gpu.global.add.u32 [%0], 1;" ::"l"(cnt + hh * 512) : "memory");
          if (lane == 0) STAMP(3, hh ? 6 : 7);
        }
        poll_ge(&P.ocnt[512 + rb * 32], 16 * (epoch + 1));
        asm volatile("fence.proxy.async.global;" ::: "memory");
        if (lane == 0) { mbar_arrive(BAR(B_O1RDY)); STAMP(2, 4); }
        __syncwarp();
      } else {
        if (PD2) __nanosleep(PD2);
        const int t = tid - 288;
        uint4 f[8];
        const float* src = P.kv + hp * 2176 + (4 * t);
        const float* zsrc = P.kv + hp * 2176 + (2048 + (t & 48) + 2 * (lane & 6));
        uint4 zp = ld_rlx4(zsrc);
#pragma unroll
        for (int p = 0; p < 8; p++) f[p] = ld_rlx4(src + 4 * ((p & 3) * 128 + (p >> 2) * 64));
        if (!opaque_true()) __trap();
#pragma unroll 1
        for (int n = 0; __any_sync(~0u, (stale8(f, tag) | (zp.x ^ tag)) & 1); n++) {
          ld_stale4(zp, zsrc, tag);
#pragma unroll
          for (int p = 0; p < 8; p++) ld_stale4(f[p], src + 4 * ((p & 3) * 128 + (p >> 2) * 64), tag);
          if (n > SPIN_LIMIT) __trap();
        }
#define PK2U(a, b) pk2(__uint_as_float(a), __uint_as_float(b))
#pragma unroll
        for (int hh = 0; hh < 2; hh++) {
          const uint4* ff = &f[4 * hh];
          uint8_t* dst = smem + OFF_KVB + hh * 2560 + q * 512 + (16 * hw + g) * 16;
          *(uint4*)dst = make_uint4(PK2U(ff[0].x, ff[0].y), PK2U(ff[1].x, ff[1].y), PK2U(ff[2].x, ff[2].y), PK2U(ff[3].x, ff[3].y));
          *(uint4*)(dst + 128) = make_uint4(PK2U(ff[0].z, ff[0].w), PK2U(ff[1].z, ff[1].w), PK2U(ff[2].z, ff[2].w), PK2U(ff[3].z, ff[3].w));
        }
        const uint32_t zf = (lane & 1) ? ((lane & 8) ? zp.w : zp.z) : ((lane & 8) ? zp.y : zp.x);
        const uint32_t zz = PK2U(zf, zf);
        *(uint4*)(smem + OFF_KVB + hw * 2560 + 2048 + lane * 16) = make_uint4(zz, zz, zz, zz);
        fence_async();
        __syncwarp();
        if (lane == 0) { mbar_arrive(BAR(B_KV)); if (hw == 0) STAMP(3, 9); }
      }
#define QBUF(ci) (sb + 2048 * (ci) + ((ci) < 6 ? OFF_STG : (ci) < 10 ? OFF_SPARE - 6 * 2048 : OFF_F2F - 10 * 2048))
      mbar_wait(BAR(B_Y), 0);
      if (elect_one()) {
        mbar_expect(sbar + 8, 4096);
#pragma unroll 1
        for (int ci = hw ? hw + 9 : 12; ci < 16; ci += 3) tma3d(QBUF(ci), &P.tmQ, 16 * cl, 64 * rank + 32, 2 * (ci & 7), sbar + 8);
      }
      mbar_wait(BAR(B_Q), 0);
      {
        const float2 sc0 = *(const float2*)(smem + OFF_SCALE + 8 * q), sc1 = *(const float2*)(smem + OFF_SCALE + 32 + 8 * q);
        const uint32_t yl = sb + OFF_XT + (lane & 7) * XT_STRIDE + (lane >> 3) * 16;
#pragma unroll 1
        for (int ci = hw; ci < 16; ci += 3) {
          const uint32_t qb = QBUF(ci);
          const int b = ci >= 10;
          mbar_wait(sbar + 8 * b, (ph >> b) & 1);
#pragma unroll 1
          for (int nl = 0; nl < 2; nl++) {
            uint32_t yy[2][4], qq[2][4];
            const uint32_t qa = qb + lane * 32 + ((lane & 4) << 2) + nl * 1024;
#pragma unroll
            for (int cg = 0; cg < 2; cg++) { ldsm4t(yy[cg], yl + cg * 2048 + (2 * ci + nl) * 64); ldsm4(qq[cg], qa ^ (cg * 16)); }
#pragma unroll
            for (int cg = 0; cg < 2; cg++) {
              const float2 sc = cg ? sc1 : sc0;
#pragma unroll
              for (int m = 0; m < 4; m++) {
                const float2 f = __half22float2(*(const __half2*)&yy[cg][m]);
                qq[cg][m] = hmul(qq[cg][m], pk2(f.x * sc.x, f.y * sc.y));
              }
              stsm4(qa ^ (cg * 16), qq[cg][0], qq[cg][1], qq[cg][2], qq[cg][3]);
            }
          }
          fence_async();
          __syncwarp();
          if (elect_one()) tma3d_st(&P.tmOA, qb, 16 * cl, 64 * rank + 32 * (ci >> 3), 2 * (ci & 7));
        }
        asm volatile("cp.async.bulk.commit_group;\ncp.async.bulk.wait_group.read 0;" ::: "memory");
      }
      if (lane == 0) STAMP(3, 10 + hw);
    }
  }
}

typedef CUresult (*EncodeFn)(CUtensorMap*, CUtensorMapDataType, cuuint32_t, void*, const cuuint64_t*, const cuuint64_t*,
                             const cuuint32_t*, const cuuint32_t*, CUtensorMapInterleave, CUtensorMapSwizzle,
                             CUtensorMapL2promotion, CUtensorMapFloatOOBfill);

static void enc(EncodeFn fn, CUtensorMap* m, const void* p, int rank, const cuuint64_t* dims, const cuuint64_t* strides,
                const cuuint32_t* box, CUtensorMapSwizzle swz, CUtensorMapL2promotion promo) {
  cuuint32_t es[4] = {1, 1, 1, 1};
  fn(m, CU_TENSOR_MAP_DATA_TYPE_BFLOAT16, rank, (void*)p, dims, strides, box, es, CU_TENSOR_MAP_INTERLEAVE_NONE, swz, promo,
     CU_TENSOR_MAP_FLOAT_OOB_FILL_NONE);
}

extern "C" void kernel_launch(void* const* d_in, const int* in_sizes, int n_in, void* d_out, int out_size) {
  void* fp = nullptr;
  cudaDriverEntryPointQueryResult qr;
  cudaGetDriverEntryPoint("cuTensorMapEncodeTiled", &fp, cudaEnableDefault, &qr);
  EncodeFn fn = (EncodeFn)fp;
  Params P;
  P.shift_k = (const __nv_bfloat16*)d_in[3]; P.h = (const __nv_bfloat16*)d_in[4]; P.D = (const __nv_bfloat16*)d_in[5];
  P.q = (const __nv_bfloat16*)d_in[0]; P.k = (const __nv_bfloat16*)d_in[1]; P.v = (const __nv_bfloat16*)d_in[2];
  cudaGetSymbolAddress((void**)&P.part, g_part); cudaGetSymbolAddress((void**)&P.kv, g_kv); cudaGetSymbolAddress((void**)&P.o, g_o);
  cudaGetSymbolAddress((void**)&P.h16, g_h16);
  cudaGetSymbolAddress((void**)&P.ocnt, g_ocnt); cudaGetSymbolAddress((void**)&P.epoch, g_epoch);
  cudaGetSymbolAddress((void**)&P.thr, c_thr); cudaGetSymbolAddress((void**)&P.img, c_img);
  P.x = (const __nv_bfloat16*)d_in[6]; P.w = (const __nv_bfloat16*)d_in[7]; P.wo = (const __nv_bfloat16*)d_in[8];
  const CUtensorMapSwizzle S128 = CU_TENSOR_MAP_SWIZZLE_128B, S32 = CU_TENSOR_MAP_SWIZZLE_32B;
  const CUtensorMapL2promotion P0 = CU_TENSOR_MAP_L2_PROMOTION_NONE, P128 = CU_TENSOR_MAP_L2_PROMOTION_L2_128B;
  { cuuint64_t d[2] = {1024, 2048}, s[1] = {2048}; cuuint32_t b[2] = {64, 128}; enc(fn, &P.tmX, d_in[6], 2, d, s, b, S128, P128); }
  { cuuint64_t d[3] = {1024, 1024, 3}, s[2] = {6144, 2048}; cuuint32_t b[3] = {64, 64, 3}; enc(fn, &P.tmW, d_in[7], 3, d, s, b, S128, P128); }
  { cuuint64_t d[4] = {64, 64, 16, 16}, s[3] = {2048, 131072, 128}; cuuint32_t b[4] = {64, 32, 2, 2}; enc(fn, &P.tmWo, d_in[8], 4, d, s, b, S128, P128); }
  { cuuint64_t d[4] = {64, 64, 16, 16}, s[3] = {2048, 131072, 128}; cuuint32_t b[4] = {64, 32, 2, 1}; enc(fn, &P.tmWo1, d_in[8], 4, d, s, b, S128, P128); }
  { cuuint64_t d[4] = {1024, 2, 256, 4}, s[3] = {2048, 16384, 4096}; cuuint32_t b[4] = {16, 2, 17, 4}; enc(fn, &P.tmK, d_in[1], 4, d, s, b, S32, PKV); }
  { cuuint64_t d[4] = {1024, 2, 256, 4}, s[3] = {2048, 16384, 4096}; cuuint32_t b[4] = {16, 2, 16, 4}; enc(fn, &P.tmV, d_in[2], 4, d, s, b, S32, PKV); }
  { cuuint64_t d[3] = {1024, 128, 16}, s[2] = {32768, 2048}; cuuint32_t b[3] = {16, 32, 2}; enc(fn, &P.tmQ, d_in[0], 3, d, s, b, S32, PKV); }
  { cuuint64_t d[3] = {1024, 128, 16}, s[2] = {65536, 4096}; cuuint32_t b[3] = {16, 32, 2}; enc(fn, &P.tmOA, d_out, 3, d, s, b, S32, P0); }
  { cuuint64_t d[2] = {2048, 2048}, s[1] = {4096}; cuuint32_t b[2] = {64, 64}; enc(fn, &P.tmOB, d_out, 2, d, s, b, S128, P0); }
  cudaFuncSetAttribute(fused_kernel, cudaFuncAttributeMaxDynamicSharedMemorySize, SMEM_TOTAL);
  fused_kernel<<<128, 384, SMEM_TOTAL>>>(P);
}
```

```cpp
#include <cuda_runtime.h>
#include <cuda_bf16.h>
#include <cuda_fp16.h>
#include <cuda.h>
#include <stdint.h>

template<int TA, int TB, int SA=1> __device__ __forceinline__ void wgmma_ss_n192(float (&d)[96], uint64_t da, uint64_t db, int scale_d) {
  asm volatile("{\n.reg .pred p;\nsetp.ne.b32 p, %98, 0;\n"
    "wgmma.mma_async.sync.aligned.m64n192k16.f32.bf16.bf16 {%0, %1, %2, %3, %4, %5, %6, %7, %8, %9, %10, %11, %12, %13, %14, %15, %16, %17, %18, %19, %20, %21, %22, %23, %24, %25, %26, %27, %28, %29, %30, %31, %32, %33, %34, %35, %36, %37, %38, %39, %40, %41, %42, %43, %44, %45, %46, %47, %48, %49, %50, %51, %52, %53, %54, %55, %56, %57, %58, %59, %60, %61, %62, %63, %64, %65, %66, %67, %68, %69, %70, %71, %72, %73, %74, %75, %76, %77, %78, %79, %80, %81, %82, %83, %84, %85, %86, %87, %88, %89, %90, %91, %92, %93, %94, %95}, %96, %97, p, %101, 1, %99, %100;\n}\n"
    : "+f"(d[0]), "+f"(d[1]), "+f"(d[2]), "+f"(d[3]), "+f"(d[4]), "+f"(d[5]), "+f"(d[6]), "+f"(d[7]), "+f"(d[8]), "+f"(d[9]), "+f"(d[10]), "+f"(d[11]), "+f"(d[12]), "+f"(d[13]), "+f"(d[14]), "+f"(d[15]), "+f"(d[16]), "+f"(d[17]), "+f"(d[18]), "+f"(d[19]), "+f"(d[20]), "+f"(d[21]), "+f"(d[22]), "+f"(d[23]), "+f"(d[24]), "+f"(d[25]), "+f"(d[26]), "+f"(d[27]), "+f"(d[28]), "+f"(d[29]), "+f"(d[30]), "+f"(d[31]), "+f"(d[32]), "+f"(d[33]), "+f"(d[34]), "+f"(d[35]), "+f"(d[36]), "+f"(d[37]), "+f"(d[38]), "+f"(d[39]), "+f"(d[40]), "+f"(d[41]), "+f"(d[42]), "+f"(d[43]), "+f"(d[44]), "+f"(d[45]), "+f"(d[46]), "+f"(d[47]), "+f"(d[48]), "+f"(d[49]), "+f"(d[50]), "+f"(d[51]), "+f"(d[52]), "+f"(d[53]), "+f"(d[54]), "+f"(d[55]), "+f"(d[56]), "+f"(d[57]), "+f"(d[58]), "+f"(d[59]), "+f"(d[60]), "+f"(d[61]), "+f"(d[62]), "+f"(d[63]), "+f"(d[64]), "+f"(d[65]), "+f"(d[66]), "+f"(d[67]), "+f"(d[68]), "+f"(d[69]), "+f"(d[70]), "+f"(d[71]), "+f"(d[72]), "+f"(d[73]), "+f"(d[74]), "+f"(d[75]), "+f"(d[76]), "+f"(d[77]), "+f"(d[78]), "+f"(d[79]), "+f"(d[80]), "+f"(d[81]), "+f"(d[82]), "+f"(d[83]), "+f"(d[84]), "+f"(d[85]), "+f"(d[86]), "+f"(d[87]), "+f"(d[88]), "+f"(d[89]), "+f"(d[90]), "+f"(d[91]), "+f"(d[92]), "+f"(d[93]), "+f"(d[94]), "+f"(d[95])
    : "l"(da), "l"(db), "r"(scale_d), "n"(TA), "n"(TB), "n"(SA));
}
template<int TA, int TB, int SA=1> __device__ __forceinline__ void wgmma_ss_n128(float (&d)[64], uint64_t da, uint64_t db, int scale_d) {
  asm volatile("{\n.reg .pred p;\nsetp.ne.b32 p, %66, 0;\n"
    "wgmma.mma_async.sync.aligned.m64n128k16.f32.bf16.bf16 {%0, %1, %2, %3, %4, %5, %6, %7, %8, %9, %10, %11, %12, %13, %14, %15, %16, %17, %18, %19, %20, %21, %22, %23, %24, %25, %26, %27, %28, %29, %30, %31, %32, %33, %34, %35, %36, %37, %38, %39, %40, %41, %42, %43, %44, %45, %46, %47, %48, %49, %50, %51, %52, %53, %54, %55, %56, %57, %58, %59, %60, %61, %62, %63}, %64, %65, p, %69, 1, %67, %68;\n}\n"
    : "+f"(d[0]), "+f"(d[1]), "+f"(d[2]), "+f"(d[3]), "+f"(d[4]), "+f"(d[5]), "+f"(d[6]), "+f"(d[7]), "+f"(d[8]), "+f"(d[9]), "+f"(d[10]), "+f"(d[11]), "+f"(d[12]), "+f"(d[13]), "+f"(d[14]), "+f"(d[15]), "+f"(d[16]), "+f"(d[17]), "+f"(d[18]), "+f"(d[19]), "+f"(d[20]), "+f"(d[21]), "+f"(d[22]), "+f"(d[23]), "+f"(d[24]), "+f"(d[25]), "+f"(d[26]), "+f"(d[27]), "+f"(d[28]), "+f"(d[29]), "+f"(d[30]), "+f"(d[31]), "+f"(d[32]), "+f"(d[33]), "+f"(d[34]), "+f"(d[35]), "+f"(d[36]), "+f"(d[37]), "+f"(d[38]), "+f"(d[39]), "+f"(d[40]), "+f"(d[41]), "+f"(d[42]), "+f"(d[43]), "+f"(d[44]), "+f"(d[45]), "+f"(d[46]), "+f"(d[47]), "+f"(d[48]), "+f"(d[49]), "+f"(d[50]), "+f"(d[51]), "+f"(d[52]), "+f"(d[53]), "+f"(d[54]), "+f"(d[55]), "+f"(d[56]), "+f"(d[57]), "+f"(d[58]), "+f"(d[59]), "+f"(d[60]), "+f"(d[61]), "+f"(d[62]), "+f"(d[63])
    : "l"(da), "l"(db), "r"(scale_d), "n"(TA), "n"(TB), "n"(SA));
}
template<int TA, int TB, int SA=1> __device__ __forceinline__ void wgmma_ss_n72(float (&d)[36], uint64_t da, uint64_t db, int scale_d) {
  asm volatile("{\n.reg .pred p;\nsetp.ne.b32 p, %38, 0;\n"
    "wgmma.mma_async.sync.aligned.m64n72k16.f32.bf16.bf16 {%0, %1, %2, %3, %4, %5, %6, %7, %8, %9, %10, %11, %12, %13, %14, %15, %16, %17, %18, %19, %20, %21, %22, %23, %24, %25, %26, %27, %28, %29, %30, %31, %32, %33, %34, %35}, %36, %37, p, %41, 1, %39, %40;\n}\n"
    : "+f"(d[0]), "+f"(d[1]), "+f"(d[2]), "+f"(d[3]), "+f"(d[4]), "+f"(d[5]), "+f"(d[6]), "+f"(d[7]), "+f"(d[8]), "+f"(d[9]), "+f"(d[10]), "+f"(d[11]), "+f"(d[12]), "+f"(d[13]), "+f"(d[14]), "+f"(d[15]), "+f"(d[16]), "+f"(d[17]), "+f"(d[18]), "+f"(d[19]), "+f"(d[20]), "+f"(d[21]), "+f"(d[22]), "+f"(d[23]), "+f"(d[24]), "+f"(d[25]), "+f"(d[26]), "+f"(d[27]), "+f"(d[28]), "+f"(d[29]), "+f"(d[30]), "+f"(d[31]), "+f"(d[32]), "+f"(d[33]), "+f"(d[34]), "+f"(d[35])
    : "l"(da), "l"(db), "r"(scale_d), "n"(TA), "n"(TB), "n"(SA));
}
template<int TB, int SA=1> __device__ __forceinline__ void wgmma_rs_n40(float (&d)[20], uint32_t a0, uint32_t a1, uint32_t a2, uint32_t a3, uint64_t db, int scale_d) {
  asm volatile("{\n.reg .pred p;\nsetp.ne.b32 p, %25, 0;\n"
    "wgmma.mma_async.sync.aligned.m64n40k16.f32.bf16.bf16 {%0, %1, %2, %3, %4, %5, %6, %7, %8, %9, %10, %11, %12, %13, %14, %15, %16, %17, %18, %19}, {%20, %21, %22, %23}, %24, p, %27, 1, %26;\n}\n"
    : "+f"(d[0]), "+f"(d[1]), "+f"(d[2]), "+f"(d[3]), "+f"(d[4]), "+f"(d[5]), "+f"(d[6]), "+f"(d[7]), "+f"(d[8]), "+f"(d[9]), "+f"(d[10]), "+f"(d[11]), "+f"(d[12]), "+f"(d[13]), "+f"(d[14]), "+f"(d[15]), "+f"(d[16]), "+f"(d[17]), "+f"(d[18]), "+f"(d[19])
    : "r"(a0), "r"(a1), "r"(a2), "r"(a3), "l"(db), "r"(scale_d), "n"(TB), "n"(SA));
}
template<int TB> __device__ __forceinline__ void wgmma_hrs_n64(uint32_t (&d)[16], uint32_t a0, uint32_t a1, uint32_t a2, uint32_t a3, uint64_t db, int scale_d) {
  asm volatile("{\n.reg .pred p;\nsetp.ne.b32 p, %21, 0;\n"
    "wgmma.mma_async.sync.aligned.m64n64k16.f16.f16.f16 {%0, %1, %2, %3, %4, %5, %6, %7, %8, %9, %10, %11, %12, %13, %14, %15}, {%16, %17, %18, %19}, %20, p, 1, 1, %22;\n}\n"
    : "+r"(d[0]), "+r"(d[1]), "+r"(d[2]), "+r"(d[3]), "+r"(d[4]), "+r"(d[5]), "+r"(d[6]), "+r"(d[7]), "+r"(d[8]), "+r"(d[9]), "+r"(d[10]), "+r"(d[11]), "+r"(d[12]), "+r"(d[13]), "+r"(d[14]), "+r"(d[15])
    : "r"(a0), "r"(a1), "r"(a2), "r"(a3), "l"(db), "r"(scale_d), "n"(TB));
}
template<int TB> __device__ __forceinline__ void wgmma_hrs_n32(uint32_t (&d)[8], uint32_t a0, uint32_t a1, uint32_t a2, uint32_t a3, uint64_t db, int scale_d) {
  asm volatile("{\n.reg .pred p;\nsetp.ne.b32 p, %13, 0;\n"
    "wgmma.mma_async.sync.aligned.m64n32k16.f16.f16.f16 {%0, %1, %2, %3, %4, %5, %6, %7}, {%8, %9, %10, %11}, %12, p, 1, 1, %14;\n}\n"
    : "+r"(d[0]), "+r"(d[1]), "+r"(d[2]), "+r"(d[3]), "+r"(d[4]), "+r"(d[5]), "+r"(d[6]), "+r"(d[7])
    : "r"(a0), "r"(a1), "r"(a2), "r"(a3), "l"(db), "r"(scale_d), "n"(TB));
}

__device__ __align__(128) const uint32_t c_thr[1536] = {
  0x33fb33ff,0xa49c9de4,0x33273352,0xaf2cae76,0x33e233f1,0xa96ca7bd,0x32c432f7,0xb045afdd,0x33b733cf,0xac3eaaf7,0x3250328c,0xb0eab099,
  0x3378339a,0xadbcacff,0x31cd3211,0xb182b137,0x33d033fb,0xaadea46a,0x299e2d17,0xb3e0b396,0x32fb337a,0xafd2adb1,0xa78b1f76,0xb3f2b3ff,
  0x318b3254,0xb1c5b0e5,0xae6bac32,0xb354b3b8,0x2f4230a3,0xb321b285,0xb133b040,0xb215b2c7,0x337c33f2,0xada5a759,0xb179afc8,0xb1d6b2fe,
  0x31463293,0xb204b08e,0xb394b2ba,0xad23b055,0x2b402f4e,0xb3cbb31e,0xb3e4b3f9,0x293ba533,0xac269c52,0xb3bab400,0xb258b357,0x30e02e5f,
  0x330133e5,0xafbda922,0xb3f3b3c9,0x2727ab59,0x2deb314a,0xb36fb200,0xb194b32f,0x31bc2f0a,0xacdb2084,0xb39fb3ff,0xa565aea4,0x33f93347,
  0xb2b6b0db,0xb05ab25c,0x30892c1a,0x329733bc,0x326033d4,0xb0d6aa94,0xb00ab29b,0x32e83084,0x20e82f64,0xb3feb318,0x2d8da597,0x338133f8,
  0xb1fcae48,0xb14fb35c,0x339031b8,0x2d3a3199,0xb3e6b3ae,0x2909ac7b,0x32d133f4,0xb030a6f5,0x319d33bf,0xb1b3ac02,0x2e3ca874,0x335e33ec,
  0xacc32b89,0xb3a3b3c6,0x33f83276,0x25c930b7,0xb3dcb1f8,0xaa01b154,0x30653335,0xb2b0aef4,0xb107b383,0x32392d81,0xafa6214d,0xb307b3fe,
  0x30bc33a5,0xb273acb7,0x33c5311b,0x2ba23229,0xb0cc94b6,0xb267b400,0x30153360,0xb2e1ae31,0xb385b3ab,0x2d76ac93,0xb166a691,0xb1e7b3f5,
  0x22deb06a,0x33fd32ac,0xb337b3da,0x2ee8aa19,0x2f853387,0xb310ad6a,0x322d33fe,0xb1162216,0xb2a9abd3,0xb06fb3c2,0xb07428a6,0xb2a5b3ea,
  0xb111b3e9,0x323128be,0xb30db3c3,0x2f90abba,0x31aa227a,0x31a633fd,0x2e25ad5e,0x33633389,0x2d6a3365,0xb387ae1a,0xa21631aa,0xb3feb1a6,
  0xb3c2af85,0xabd3b310,0xb3eab22d,0x28a6b116,0xa8beb2a9,0x33e9306f,0x2bbab074,0x33c332a5,0x33fd3111,0x227a3231,0x3389330d,0xad5e2f90,
  0x2a63333f,0xb3d7aec6,0xb2a2a1b1,0xb07ab3fe,0xb3f7b158,0x25fbb1f4,0xacb7b38b,0x33a52d52,0x2e0eb025,0x336832d8,0x340030bc,0x14b63273,
  0x323533c0,0xb10c2beb,0xac9330cc,0xb3abb267,0x23433316,0xb3fdaf6f,0xb38eb225,0x2d46b11f,0xb342b29e,0x2ebbb07f,0x31e3aa7c,0x316b33d6,
  0x3264a6c3,0x30d133f5,0x2c0233ac,0xb3bfac87,0x28f0336a,0xb3e7ae02,0xb3c6b19d,0x2b89b1b3,0xa59732e8,0xb3f8b00a,0xaccfb3ed,0x33a1285b,
  0xb1b8b381,0x3199ad8d,0x336c31df,0xadf73170,0x33f42d3a,0x26f53390,0xb30423a7,0xafb2b3fc,0xb05f3030,0xb2b3b2d1,0x29e8b27a,0x33dd30b2,
  0xab5932b6,0xb3c9b05a,0x30adb089,0x327e3297,0xaf0ab3f3,0x332fa727,0x240633b0,0xb3fcac6f,0x33473194,0xaea431bc,0xb174b359,0x31daae54,
  0xb3bca565,0xac1ab3f9,0x33ee2f59,0xa842331b,0xaddf3281,0xb371b0a8,0x34002b40,0x1c5233cb,0xa759b3ef,0x33f22829,0xb2fe2c26,0xafc8b3ba,
  0x308e337c,0xb2932da5,0x3055b179,0x32ba31d6,0xb31eb146,0x2f4eb204,0xa5333394,0xb3f9ad23,0xaff33249,0xb2f1b0f3,0x30e532fb,0xb2542fd2,
  0x2b28b373,0x33cc2dd4,0xb285b18b,0x30a3b1c5,0x246a33fa,0xb3fba500,0x33962f42,0xad173321,0xadb1b3d0,0x337aaade,0xb3ffa99e,0x1f76b3e0,
  0xb0ee320d,0xb24db13c,0xac4b3398,0xb3b5ad0b,0x304ab289,0x32c1309e,0x2985b3ce,0x33e12b0f,0xaf3732f4,0xb324afe8,0xa4ce33f0,0xb3faa7ef,
  0x2dc8b34f,0x33762e82,0x9de4b3ff,0x33ff1ead,0xb1c931cd,0xb186b182,0xb3762e82,0xadc8b34f,0x324db13c,0x30ee320d,0x33b5ad0b,0x2c4b3398,
  0xb2c1309e,0xb04ab289,0xb3e12b0f,0xa985b3ce,0x3324afe8,0x2f3732f4,0x33faa7ef,0x24ce33f0,0xb285318b,0xb0a3b1c5,0xb2c7ae6b,0x3040b354,
  0x3396af42,0x2d173321,0x31413133,0xb2093215,0xb3ff299e,0x9f76b3e0,0xae8db2bd,0x334cb050,0x33b8278b,0xac3233f2,0x281033b3,0xb3ef2c57,
  0xb31e3146,0xaf4eb204,0xa533b394,0x33f9ad23,0x3400ab40,0x9c5233cb,0xae5f33e4,0xb357a93b,0xb2feac26,0x2fc8b3ba,0x3245b258,0x30f830e0,
  0x30553179,0xb2ba31d6,0xb3df2e99,0xa9b6b34a,0xb39230fd,0xad2fb241,0x3200b301,0x314a2fbd,0x337f1b11,0xad993400,0xb3ff2deb,0xa084b36f,
  0xb005b129,0x32ebb21d,0x325c2cdb,0xb0db339f,0xa92233de,0xb3e529cf,0xab59b2b6,0x33c9b05a,0xb3dd30b2,0xa9e8b27a,0x33d4ab71,0xaa9433c8,
  0x32212c0e,0xb12433bd,0xaf64b0d6,0x3318b260,0x197fb345,0x3400aeaf,0xae4833fe,0xb35c20e8,0xb23d3332,0xb102aeff,0x33aeb14f,0x2c7b31fc,
  0xb3fe3065,0xa14db2b0,0x2ebb307f,0xb342329e,0x300f2fa6,0xb2e53307,0x30d1b3f5,0x326426c3,0x302ab400,0x32d517db,0xb3e72e02,0x28f0b36a,
  0xb3fd2f6f,0x2343b316,0x2d46311f,0xb38e3225,0xb3f53015,0x2691b2e1,0xaf9b33eb,0xb30a288d,0x2a193166,0xb3da31e7,0x33d7aec6,0xaa63333f,
  0x3313b337,0x2f7a2ee8,0xa5fbb1f4,0x33f7b158,0xb1a1a8d7,0x31afb3e8,0xb36832d8,0xae0eb025,0xb3c22f85,0x2bd3b310,0xb3ea322d,0xa8a6b116,
  0xa8be32a9,0xb3e9306f,0x2bba3074,0xb3c332a5,0x33fdb111,0xa27a3231,0x3389b30d,0x2d5e2f90,0xa216b1aa,0x33feb1a6,0xaed2ae25,0x333db363,
  0xb3652edd,0x2e1ab33a,0xb1aa227a,0x31a6b3fd,0xaf853387,0xb3102d6a,0xb22d33fe,0xb116a216,0x32a9abd3,0xb06f33c2,0x307428a6,0xb2a533ea,
  0x3111b3e9,0x3231a8be,0x330db3c3,0x2f902bba,0xb2e12e31,0x3015b360,0x288db1a1,0x33ebb1af,0xb1e733f5,0xb1662691,0xb33f2f9b,0x2ec6b30a,
  0x2ee82a19,0xb33733da,0xb15833d7,0xb1f42a63,0x33e8b313,0x28d72f7a,0x302525fb,0xb2d833f7,0xb2392d81,0x3107b383,0x3307b3fe,0x2fa6214d,
  0xb35e33ec,0xae3ca874,0x97dbb00f,0x3400b2e5,0xa5c930b7,0xb3f83276,0xb316302a,0x2f6fb2d5,0x32b0aef4,0xb0653335,0xb29e33fd,0xb07f2343,
  0xb1702ccf,0x31dfb3a1,0x3345b124,0xaeaf3221,0xb3fc336c,0xa3a7adf7,0x3332b400,0x2eff997f,0xb0b23304,0xb27a2fb2,0x2b71b102,0x33c8b23d,
  0x2c0e29e8,0xb3bd33dd,0xb0d62a94,0x3260b3d4,0xb0892c1a,0x3297b3bc,0x2aad2842,0xb3d333ee,0xb3b0327e,0x2c6fb0ad,0x3241b035,0xb0fd32ce,
  0xb35933fc,0xae542406,0x3400b392,0x1b112d2f,0xaf5931da,0xb31b3174,0x321db37f,0x3129ad99,0xaf152ac6,0x332cb3d2,0xb1463293,0xb204308e,
  0xb281312e,0x30a8b219,0xab402f4e,0xb3cb331e,0xb3ef3371,0x2829addf,0x2c269c52,0xb3ba3400,0xb37c33f2,0xada52759,0x3179afc8,0xb1d632fe,
  0xacf32953,0x339cb3e3,0xb3fa33cc,0x2500ab28,0xb0942f21,0x3290b32a,0xb3d033fb,0xaade246a,0xb249317d,0x30f3b1d2,0xb2fb337a,0xafd22db1,
  0xb37332f1,0x2dd4aff3,0xb18b3254,0xb1c530e5,0xa96c27bd,0x33e2b3f1,0xb0452fdd,0x32c4b2f7,0xac3e2af7,0x33b7b3cf,0xb0ea3099,0x3250b28c,
  0xadbc2cff,0x3378b39a,0xb1823137,0x31cdb211,0xaf2c2e76,0x3327b352,0xb20d31c9,0x313cb186,0x313c3186,0xb20db1c9,0x2d0b2dc8,0xb398b376,
  0x309e30ee,0xb289b24d,0x2b0f2c4b,0xb3ceb3b5,0x2fe8304a,0xb2f4b2c1,0x27ef2985,0xb3f0b3e1,0x2e822f37,0xb34fb324,0x1ead24ce,0xb3ffb3fa,
  0xb2bdb209,0xb050b141,0xb290b32a,0x30942f21,0xb3b3b34c,0xac57ae8d,0xb0f3b1d2,0x3249317d,0xb400b3ef,0x1d1ba810,0xadd4aff3,0x337332f1,
  0xb39cb3e3,0x2cf32953,0xa500ab28,0x33fa33cc,0xae99b0f8,0x334a3245,0x33ff33b2,0x201f2c63,0x2438a9b6,0x33fc33df,0x332c33d2,0xaf15aac6,
  0x303a2ce7,0x32cb339e,0x30a83219,0xb281b12e,0x32ee31c0,0x2ffe3190,0x28292ddf,0xb3efb371,0x33b0327e,0x2c6f30ad,0xb241b035,0xb0fdb2ce,
  0x335933fc,0xae54a406,0xb400b392,0x1b11ad2f,0x2f5931da,0xb31bb174,0xb21db37f,0x31292d99,0xaaad2842,0xb3d3b3ee,0xa9cfb005,0x33de32eb,
  0x285b305f,0xb3edb2b3,0x2c0ea9e8,0x33bd33dd,0xb170accf,0xb1dfb3a1,0x33453124,0x2eaf3221,0xb3fcb36c,0x23a7adf7,0x33323400,0xaeff997f,
  0xb0b2b304,0x327a2fb2,0x2b713102,0xb3c8b23d,0xb400b2e5,0x17dbb00f,0x2e023264,0xb36ab0d1,0xaf6fb2d5,0x3316302a,0xb11fa8f0,0xb225b3e7,
  0x307f2343,0x329e33fd,0xb3d6b38e,0x2a7cad46,0x33f53342,0xa6c32ebb,0xac87b1e3,0x33ac316b,0x28d7af7a,0x33e83313,0xb2d8b3f7,0x3025a5fb,
  0x33eb31af,0x288d31a1,0x2bebae0e,0x33c03368,0x2ec6330a,0xb33faf9b,0x33fe3235,0x21b1310c,0xb1f4aa63,0xb158b3d7,0x2d5232a2,0xb38bb07a,
  0x33a7333d,0xacab2ed2,0x33f63162,0x262d31eb,0xaa4b301a,0xb3d8b2de,0x2a32326b,0xb3d9b0c7,0xb3f6b26f,0x265fb0c1,0xb3a9b020,0xac9fb2db,
  0x0e48b15d,0x340031f0,0xae1ab33a,0x33652edd,0xaed22e25,0xb33db363,0xb1eb0e48,0xb162b400,0xb2deb3a7,0x301aacab,0xb0c7b3f6,0x326b262d,
  0x30c1aa4b,0x326f33d8,0x32db2a32,0x302033d9,0x31f033f6,0xb15d265f,0x2edd33a9,0xb33aac9f,0xb2acb385,0x306aad76,0x2a19b166,0x33da31e7,
  0x3229a2de,0x311b33fd,0x33133337,0xaf7a2ee8,0x2e3133c5,0xb360aba2,0xb1a128d7,0xb1afb3e8,0xb3f5b015,0xa691b2e1,0xaf9bb3eb,0x330a288d,
  0x3154acc3,0x31f833a3,0x2ef433f8,0xb335a5c9,0x2d8133dc,0xb383aa01,0xb3feb065,0x214db2b0,0xb3ecb107,0x2874b239,0x300fafa6,0x32e53307,
  0x30b7ae3c,0x3276335e,0x302a3400,0xb2d517db,0x312433bd,0xb2212c0e,0xb318b260,0x2f64b0d6,0xb400aeaf,0x997fb345,0x335c20e8,0x2e4833fe,
  0x3102aeff,0x323d3332,0xac7b31fc,0xb3aeb14f,0x2a9433c8,0xb3d4ab71,0xb084b3e6,0x329ba909,0xb2ce2aad,0xb035b3d3,0x33e529cf,0x292233de,
  0x2d2fb241,0x339230fd,0xb14a2fbd,0xb200b301,0x2d993400,0xb37f1b11,0x2084b36f,0x33ff2deb,0xb2ebb21d,0x3005b129,0x30db339f,0xb25c2cdb,
  0xae5fb3e4,0x3357a93b,0xb190303a,0xb1c0b2cb,0x32453258,0xb0f830e0,0x2c63b2ee,0x33b22ffe,0xb3dfae99,0x29b6b34a,0x2ac633ff,0xb3d2a01f,
  0x339ea438,0x2ce733fc,0xb12eb32c,0x3219af15,0x33b8a78b,0x2c3233f2,0x2810b3b3,0x33ef2c57,0xb2c72e6b,0xb040b354,0x29533400,0xb3e31d1b,
  0x3141b133,0x32093215,0xaf21b39c,0x332aacf3,0xae8d32bd,0xb34cb050,0x317d3290,0xb1d23094,0x27bd33fb,0xb3f1249c,0x2fdd3327,0xb2f72f2c,
  0xaaf7b3e2,0x33cfa96c,0xb099b2c4,0x328cb045,0x2cff33b7,0xb39a2c3e,0x31373250,0xb21130ea,0xae76b378,0x3352adbc,0xb1c9b1cd,0x3186b182,
  0xb3ff1ead,0x1de4b3ff,0xb352adbc,0x2e76b378,0x33f1249c,0xa7bd33fb,0x32f72f2c,0xafdd3327,0xb3cfa96c,0x2af7b3e2,0xb28cb045,0x3099b2c4,
  0x339a2c3e,0xacff33b7,0x321130ea,0xb1373250,0x2953b400,0x33e31d1b,0x33ccadd4,0x2b283373,0xaf21339c,0xb32aacf3,0xb3fb2500,0x246ab3fa,
  0x317db290,0x31d23094,0x337a2ade,0xadb133d0,0xb2f130f3,0xaff3b249,0xb254afd2,0x30e5b2fb,0x339e2438,0xace733fc,0xb12e332c,0xb219af15,
  0xb190b03a,0x31c0b2cb,0x3371b0a8,0x2ddf3281,0x2c6332ee,0xb3b22ffe,0xb3f22829,0x2759b3ef,0x2ac6b3ff,0x33d2a01f,0x32932da5,0xb08e337c,
  0xaf0a33f3,0xb32fa727,0x2406b3b0,0x33fcac6f,0x3347b194,0x2ea431bc,0xb1743359,0xb1daae54,0xb3bc2565,0x2c1ab3f9,0x33eeaf59,0x2842331b,
  0x30ad3089,0xb27e3297,0xb2ceaaad,0x3035b3d3,0xb29ba909,0x3084b3e6,0x305f3030,0xb2b332d1,0x259732e8,0xb3f8300a,0x2ccfb3ed,0x33a1a85b,
  0x31b8b381,0x31992d8d,0xb36c31df,0xadf7b170,0xb3f42d3a,0x26f5b390,0x330423a7,0xafb233fc,0x316bb3d6,0x31e32a7c,0xb3832a01,0x2d81b3dc,
  0xb3bf2c87,0x2c02b3ac,0x28743239,0xb3ec3107,0x2b8931b3,0xb3c6319d,0x3276b35e,0x30b72e3c,0x31f8b3a3,0x31542cc3,0xb33525c9,0x2ef4b3f8,
  0x310c2beb,0xb23533c0,0x33abb267,0x2c9330cc,0x307ab3fe,0x32a2a1b1,0xb06aad76,0x32acb385,0xb3a52d52,0x2cb7b38b,0xb11b33fd,0xb229a2de,
  0x94b63273,0xb40030bc,0x3360aba2,0xae3133c5,0xb2de33a7,0xb01aacab,0xb0c733f6,0xb26b262d,0x30c12a4b,0xb26f33d8,0x32dbaa32,0xb02033d9,
  0x31f0b3f6,0x315d265f,0x2eddb3a9,0x333aac9f,0xb1eb8e48,0x3162b400,0xb3872e1a,0x2d6ab365,0xae25ad5e,0x3363b389,0x8e48b15d,0x3400b1f0,
  0xb3a7333d,0xacabaed2,0xb3f63162,0x262db1eb,0x2a4b301a,0xb3d832de,0xaa32326b,0xb3d930c7,0x33f6b26f,0x265f30c1,0x33a9b020,0xac9f32db,
  0x33c0b368,0x2beb2e0e,0x30cc94b6,0xb2673400,0x21b1b10c,0x33feb235,0x3385b3ab,0x2d762c93,0xb38b307a,0x2d52b2a2,0xa2deb06a,0x33fdb2ac,
  0xb0bc33a5,0xb2732cb7,0xb3c5311b,0x2ba2b229,0x26c32ebb,0xb3f53342,0xb3ac316b,0x2c87b1e3,0x336ab0d1,0xae023264,0xb19d33bf,0xb1b32c02,
  0x3225b3e7,0x311fa8f0,0x2cc32b89,0xb3a333c6,0xaa7cad46,0x33d6b38e,0x33dcb1f8,0xaa013154,0xb3fe3318,0x20e8af64,0x3381b3f8,0x2d8d2597,
  0xb14f335c,0xb1fc2e48,0x2d3ab199,0x3390b1b8,0x29092c7b,0xb3e633ae,0xb03026f5,0x32d1b3f4,0x32e8b084,0xb00a329b,0xb3ed32b3,0x285bb05f,
  0x29cfb005,0x33deb2eb,0xb05a325c,0xb2b630db,0xafbd2922,0x3301b3e5,0x27272b59,0xb3f333c9,0xb36f3200,0x2debb14a,0x31bcaf0a,0xb194332f,
  0xb39f33ff,0xacdba084,0x33f9b347,0xa5652ea4,0x3394b2ba,0xad233055,0xa438a9b6,0x33fcb3df,0x33e4b3f9,0x293b2533,0xb03a2ce7,0x32cbb39e,
  0x3258b357,0x30e0ae5f,0xb2ee31c0,0x2ffeb190,0x2e99b0f8,0x334ab245,0xb3ff33b2,0x201fac63,0xaf4230a3,0xb3213285,0x3133b040,0xb21532c7,
  0xa99e2d17,0xb3e03396,0x32bdb209,0xb0503141,0x278b1f76,0xb3f233ff,0x33b3b34c,0xac572e8d,0x2e6bac32,0xb35433b8,0x3400b3ef,0x1d1b2810,
  0xb289324d,0x309eb0ee,0xb3ce33b5,0x2b0fac4b,0xb2f432c1,0x2fe8b04a,0xb3f033e1,0x27efa985,0xb34f3324,0x2e82af37,0xb3ff33fa,0x1eada4ce,
  0xb3983376,0x2d0badc8,0xb3fb33ff,0xa49c1de4,0x351c35f6,0xac93a617,0xb8a3b93c,0x308d2a16,0x32f43448,0xb160afa5,0xb6a4b7fe,0x353a3389,
  0x2fa53160,0xb448b2f4,0xb389b53a,0x37fe36a4,0x26172c93,0xb5f6b51c,0xaa16b08d,0x393c38a3,0x34c3358c,0xac47a5b2,0xb85fb8f3,0x304229b1,
  0x327e33fd,0xb106af26,0xb63cb785,0x34e7330f,0x2f263106,0xb3fdb27e,0xb30fb4e7,0x3785363c,0x25b22c47,0xb58cb4c3,0xa9b1b042,0x38f3385f,
  0x346a3523,0xabf6a54d,0xb81ab8a8,0x2fef294d,0x3209336b,0xb0acaea7,0xb5d4b70a,0x34933294,0x2ea730ac,0xb36bb209,0xb294b493,0x370a35d4,
  0x254d2bf6,0xb523b46a,0xa94dafef,0x38a8381a,0x341334bc,0xab5fa4e9,0xb7a6b85a,0x2f5928e8,0x319432da,0xb052ae28,0xb56ab68d,0x343e3219,
  0x2e283052,0xb2dab194,0xb219b43e,0x368d356a,0x24e92b5f,0xb4bcb413,0xa8e8af59,0x385a37a6,0x33783456,0xaac8a484,0xb715b80a,0x2ec32884,
  0x3120324a,0xaff2ada9,0xb4ffb60e,0x33d3319e,0x2da92ff2,0xb24ab120,0xb19eb3d3,0x360e34ff,0x24842ac8,0xb456b378,0xa884aec3,0x380a3715,
  0x32cd33e3,0xaa31a420,0xb682b76f,0x2e2d281f,0x30ac31bb,0xaf3fad2a,0xb493b58d,0x33283122,0x2d2a2f3f,0xb1bbb0ac,0xb122b328,0x358d3493,
  0x24202a31,0xb3e3b2cd,0xa81fae2d,0x376f3682,0x3223331c,0xa999a376,0xb5ebb6c6,0x2d972776,0x3039312d,0xae8dacac,0xb426b50b,0x327c30a6,
  0x2cac2e8d,0xb12db039,0xb0a6b27c,0x350b3426,0x23762999,0xb31cb223,0xa776ad97,0x36c635eb,0x317a3257,0xa902a2ad,0xb552b61a,0x2d0026ad,
  0x2f8c309f,0xaddcac2e,0xb371b487,0x31cf3029,0x2c2e2ddc,0xb09faf8c,0xb029b1cf,0x34873371,0x22ad2902,0xb257b17a,0xa6adad00,0x361a3552,
  0x30d23194,0xa86ba1e4,0xb4b7b56a,0x2c6a25e4,0x2ea73012,0xad2aab5f,0xb294b402,0x31222f59,0x2b5f2d2a,0xb012aea7,0xaf59b122,0x34023294,
  0x21e4286b,0xb194b0d2,0xa5e4ac6a,0x356a34b7,0x302c30d2,0xa7a9a11b,0xb41ab4b7,0x2ba7251b,0x2dc22f0c,0xac79aa63,0xb1b6b2f7,0x30742e5f,
  0x2a632c79,0xaf0cadc2,0xae5fb074,0x32f731b6,0x211b27a9,0xb0d2b02c,0xa51baba7,0x34b7341a,0x2f0c3012,0xa67ba052,0xb2f7b402,0x2a7a2452,
  0x2cde2df5,0xab91a967,0xb0d7b1e8,0x2f8b2d65,0x29672b91,0xadf5acde,0xad65af8b,0x31e830d7,0x2052267b,0xb012af0c,0xa452aa7a,0x340232f7,
  0x2dc22ea7,0xa54d9f12,0xb1b6b294,0x294d2311,0x2bf62cde,0xaa31a86b,0xafefb0d7,0x2e2d2c6a,0x286b2a31,0xacdeabf6,0xac6aae2d,0x30d72fef,
  0x1f12254d,0xaea7adc2,0xa311a94d,0x329431b6,0x2c792d2a,0xa4209d7f,0xb074b122,0x281f217f,0x2a312b91,0xa8d0a6e0,0xae2daf8b,0x2cce2ade,
  0x26e028d0,0xab91aa31,0xaadeacce,0x2f8b2e2d,0x1d7f2420,0xad2aac79,0xa17fa81f,0x31223074,0x2a632b5f,0xa1e49bdb,0xae5faf59,0x25e41fdb,
  0x286b2967,0xa6e0a4e9,0xac6aad65,0x2ade28e8,0x24e926e0,0xa967a86b,0xa8e8aade,0x2d652c6a,0x1bdb21e4,0xab5faa63,0x9fdba5e4,0x2f592e5f,
  0x27a9286b,0x9f1298b6,0xaba7ac6a,0x23111cb6,0x254d267b,0xa420a1e4,0xa94daa7a,0x281f25e4,0x21e42420,0xa67ba54d,0xa5e4a81f,0x2a7a294d,
  0x18b61f12,0xa86ba7a9,0x9cb6a311,0x2c6a2ba7,0x211b21e4,0x98b69248,0xa51ba5e4,0x1cb61648,0x1f122052,0x9d7f9bdb,0xa311a452,0x217f1fdb,
  0x1bdb1d7f,0xa0529f12,0x9fdba17f,0x24522311,0x124818b6,0xa1e4a11b,0x96489cb6,0x25e4251b,0xa11ba1e4,0x18b61248,0x251b25e4,0x9cb69648,
  0x9f12a052,0x1d7f1bdb,0x23112452,0xa17f9fdb,0x9bdb9d7f,0x20521f12,0x1fdb217f,0xa452a311,0x924898b6,0x21e4211b,0x16481cb6,0xa5e4a51b,
  0xa7a9a86b,0x1f1218b6,0x2ba72c6a,0xa3119cb6,0xa54da67b,0x242021e4,0x294d2a7a,0xa81fa5e4,0xa1e4a420,0x267b254d,0x25e4281f,0xaa7aa94d,
  0x98b69f12,0x286b27a9,0x1cb62311,0xac6aaba7,0xaa63ab5f,0x21e41bdb,0x2e5f2f59,0xa5e49fdb,0xa86ba967,0x26e024e9,0x2c6a2d65,0xaadea8e8,
  0xa4e9a6e0,0x2967286b,0x28e82ade,0xad65ac6a,0x9bdba1e4,0x2b5f2a63,0x1fdb25e4,0xaf59ae5f,0xac79ad2a,0x24201d7f,0x30743122,0xa81fa17f,
  0xaa31ab91,0x28d026e0,0x2e2d2f8b,0xacceaade,0xa6e0a8d0,0x2b912a31,0x2ade2cce,0xaf8bae2d,0x9d7fa420,0x2d2a2c79,0x217f281f,0xb122b074,
  0xadc2aea7,0x254d1f12,0x31b63294,0xa94da311,0xabf6acde,0x2a31286b,0x2fef30d7,0xae2dac6a,0xa86baa31,0x2cde2bf6,0x2c6a2e2d,0xb0d7afef,
  0x9f12a54d,0x2ea72dc2,0x2311294d,0xb294b1b6,0xaf0cb012,0x267b2052,0x32f73402,0xaa7aa452,0xacdeadf5,0x2b912967,0x30d731e8,0xaf8bad65,
  0xa967ab91,0x2df52cde,0x2d652f8b,0xb1e8b0d7,0xa052a67b,0x30122f0c,0x24522a7a,0xb402b2f7,0xb02cb0d2,0x27a9211b,0x341a34b7,0xaba7a51b,
  0xadc2af0c,0x2c792a63,0x31b632f7,0xb074ae5f,0xaa63ac79,0x2f0c2dc2,0x2e5f3074,0xb2f7b1b6,0xa11ba7a9,0x30d2302c,0x251b2ba7,0xb4b7b41a,
  0xb0d2b194,0x286b21e4,0x34b7356a,0xac6aa5e4,0xaea7b012,0x2d2a2b5f,0x32943402,0xb122af59,0xab5fad2a,0x30122ea7,0x2f593122,0xb402b294,
  0xa1e4a86b,0x319430d2,0x25e42c6a,0xb56ab4b7,0xb17ab257,0x290222ad,0x3552361a,0xad00a6ad,0xaf8cb09f,0x2ddc2c2e,0x33713487,0xb1cfb029,
  0xac2eaddc,0x309f2f8c,0x302931cf,0xb487b371,0xa2ada902,0x3257317a,0x26ad2d00,0xb61ab552,0xb223b31c,0x29992376,0x35eb36c6,0xad97a776,
  0xb039b12d,0x2e8d2cac,0x3426350b,0xb27cb0a6,0xacacae8d,0x312d3039,0x30a6327c,0xb50bb426,0xa376a999,0x331c3223,0x27762d97,0xb6c6b5eb,
  0xb2cdb3e3,0x2a312420,0x3682376f,0xae2da81f,0xb0acb1bb,0x2f3f2d2a,0x3493358d,0xb328b122,0xad2aaf3f,0x31bb30ac,0x31223328,0xb58db493,
  0xa420aa31,0x33e332cd,0x281f2e2d,0xb76fb682,0xb378b456,0x2ac82484,0x3715380a,0xaec3a884,0xb120b24a,0x2ff22da9,0x34ff360e,0xb3d3b19e,
  0xada9aff2,0x324a3120,0x319e33d3,0xb60eb4ff,0xa484aac8,0x34563378,0x28842ec3,0xb80ab715,0xb413b4bc,0x2b5f24e9,0x37a6385a,0xaf59a8e8,
  0xb194b2da,0x30522e28,0x356a368d,0xb43eb219,0xae28b052,0x32da3194,0x3219343e,0xb68db56a,0xa4e9ab5f,0x34bc3413,0x28e82f59,0xb85ab7a6,
  0xb46ab523,0x2bf6254d,0x381a38a8,0xafefa94d,0xb209b36b,0x30ac2ea7,0x35d4370a,0xb493b294,0xaea7b0ac,0x336b3209,0x32943493,0xb70ab5d4,
  0xa54dabf6,0x3523346a,0x294d2fef,0xb8a8b81a,0xb4c3b58c,0x2c4725b2,0x385f38f3,0xb042a9b1,0xb27eb3fd,0x31062f26,0x363c3785,0xb4e7b30f,
  0xaf26b106,0x33fd327e,0x330f34e7,0xb785b63c,0xa5b2ac47,0x358c34c3,0x29b13042,0xb8f3b85f,0xb51cb5f6,0x2c932617,0x38a3393c,0xb08daa16,
  0xb2f4b448,0x31602fa5,0x36a437fe,0xb53ab389,0xafa5b160,0x344832f4,0x3389353a,0xb7feb6a4,0xa617ac93,0x35f6351c,0x2a16308d,0xb93cb8a3,
};
__device__ __align__(128) const uint32_t c_img[2560] = {
  0x326d31ed,0x333b32dd,0x33c33388,0x33fe33ea,0x33c331ed,0x31ed33c3,0xa8b22d64,0xb33bb0c4,0x33ea31ed,0xad64301d,0xb2ddb388,0x315fa8b2,
  0x32dd31ed,0xb3feabc6,0x326dad64,0xad64326d,0x30c431ed,0xaed7b2dd,0x2bc63388,0xa248b3ea,0x2bc631ed,0x315fb3c3,0xb3ea2d64,0x2ed730c4,
  0xa8b231ed,0x3388b01d,0x301db388,0xb1ed28b2,0xb01d31ed,0x22482bc6,0x30c4ad64,0x3388b26d,0x33ea33fe,0x338833c3,0x32dd333b,0x31ed326d,
  0xb2ddb3fe,0xa248b01d,0x326d2ed7,0x338833ea,0x30c433fe,0xb33babc6,0xabc6b33b,0x33fe30c4,0xabc6b3fe,0x31ed32dd,0xb3eaaed7,0x333ba8b2,
  0xa8b233fe,0x2d64b3c3,0xb01d333b,0x315fb26d,0x301db3fe,0xb3fe301d,0x30c42ed7,0x2d64b3ea,0xb26d33fe,0x2ed72bc6,0x33c3b33b,0xa248b0c4,
  0x33c3b3fe,0x315fb2dd,0x28b2aed7,0xaed728b2,0xb0c4b15f,0xaed7b01d,0xabc6ad64,0xa248a8b2,0xabc6b15f,0x315f2bc6,0x33ea3388,0x2ed7326d,
  0x28b2b15f,0x338832dd,0xb01d2d64,0xb1edb3ea,0x301db15f,0x224833c3,0xb0c4b388,0x338830c4,0x326db15f,0xb33b301d,0x33c3ad64,0xb3fe28b2,
  0x33c3b15f,0xb1edabc6,0xa8b23388,0x333bb26d,0x33eab15f,0x2d64b2dd,0xb2dd2d64,0xb15f33ea,0x32ddb15f,0x33feb3c3,0x326db388,0x2d64b0c4,
  0x28b22248,0x2d642bc6,0x301d2ed7,0x315f30c4,0xb01da248,0xb3feb2dd,0xb0c4b33b,0x2d64a8b2,0x326d2248,0x2ed733c3,0xb3c3aed7,0xa248b26d,
  0xb3c3a248,0x315fb01d,0xa8b2333b,0xaed7b3ea,0x33ea2248,0xb388abc6,0x32dd2ed7,0xb1edb0c4,0xb2dda248,0x224832dd,0x326db33b,0xb38828b2,
  0x30c42248,0x333bb3c3,0xabc6aed7,0xb3fe326d,0xabc6a248,0xb1ed301d,0xb3ea333b,0xb33b33ea,0xb26d31ed,0xb33b32dd,0xb3c33388,0xb3fe33ea,
  0xb3c331ed,0xb1ed33c3,0x28b22d64,0x333bb0c4,0xb3ea31ed,0x2d64301d,0x32ddb388,0xb15fa8b2,0xb2dd31ed,0x33feabc6,0xb26dad64,0x2d64326d,
  0xb0c431ed,0x2ed7b2dd,0xabc63388,0x2248b3ea,0xabc631ed,0xb15fb3c3,0x33ea2d64,0xaed730c4,0x28b231ed,0xb388b01d,0xb01db388,0x31ed28b2,
  0x301d31ed,0xa2482bc6,0xb0c4ad64,0xb388b26d,0xb3ea33fe,0xb38833c3,0xb2dd333b,0xb1ed326d,0x32ddb3fe,0x2248b01d,0xb26d2ed7,0xb38833ea,
  0xb0c433fe,0x333babc6,0x2bc6b33b,0xb3fe30c4,0x2bc6b3fe,0xb1ed32dd,0x33eaaed7,0xb33ba8b2,0x28b233fe,0xad64b3c3,0x301d333b,0xb15fb26d,
  0xb01db3fe,0x33fe301d,0xb0c42ed7,0xad64b3ea,0x326d33fe,0xaed72bc6,0xb3c3b33b,0x2248b0c4,0xb3c3b3fe,0xb15fb2dd,0xa8b2aed7,0x2ed728b2,
  0x30c4b15f,0x2ed7b01d,0x2bc6ad64,0x2248a8b2,0x2bc6b15f,0xb15f2bc6,0xb3ea3388,0xaed7326d,0xa8b2b15f,0xb38832dd,0x301d2d64,0x31edb3ea,
  0xb01db15f,0xa24833c3,0x30c4b388,0xb38830c4,0xb26db15f,0x333b301d,0xb3c3ad64,0x33fe28b2,0xb3c3b15f,0x31edabc6,0x28b23388,0xb33bb26d,
  0xb3eab15f,0xad64b2dd,0x32dd2d64,0x315f33ea,0xb2ddb15f,0xb3feb3c3,0xb26db388,0xad64b0c4,0xa8b22248,0xad642bc6,0xb01d2ed7,0xb15f30c4,
  0x301da248,0x33feb2dd,0x30c4b33b,0xad64a8b2,0xb26d2248,0xaed733c3,0x33c3aed7,0x2248b26d,0x33c3a248,0xb15fb01d,0x28b2333b,0x2ed7b3ea,
  0xb3ea2248,0x3388abc6,0xb2dd2ed7,0x31edb0c4,0x32dda248,0xa24832dd,0xb26db33b,0x338828b2,0xb0c42248,0xb33bb3c3,0x2bc6aed7,0x33fe326d,
  0x2bc6a248,0x31ed301d,0x33ea333b,0x333b33ea,0x30c4315f,0x2ed7301d,0x2bc62d64,0x224828b2,0x2bc6315f,0xb15fabc6,0xb3eab388,0xaed7b26d,
  0xa8b2315f,0xb388b2dd,0x301dad64,0x31ed33ea,0xb01d315f,0xa248b3c3,0x30c43388,0xb388b0c4,0xb26d315f,0x333bb01d,0xb3c32d64,0x33fea8b2,
  0xb3c3315f,0x31ed2bc6,0x28b2b388,0xb33b326d,0xb3ea315f,0xad6432dd,0x32ddad64,0x315fb3ea,0xb2dd315f,0xb3fe33c3,0xb26d3388,0xad6430c4,
  0xa8b2a248,0xad64abc6,0xb01daed7,0xb15fb0c4,0x301d2248,0x33fe32dd,0x30c4333b,0xad6428b2,0xb26da248,0xaed7b3c3,0x33c32ed7,0x2248326d,
  0x33c32248,0xb15f301d,0x28b2b33b,0x2ed733ea,0xb3eaa248,0x33882bc6,0xb2ddaed7,0x31ed30c4,0x32dd2248,0xa248b2dd,0xb26d333b,0x3388a8b2,
  0xb0c4a248,0xb33b33c3,0x2bc62ed7,0x33feb26d,0x2bc62248,0x31edb01d,0x33eab33b,0x333bb3ea,0x326d31ed,0x333b32dd,0x33c33388,0x33fe33ea,
  0x33c331ed,0x31ed33c3,0xa8b22d64,0xb33bb0c4,0x33ea31ed,0xad64301d,0xb2ddb388,0x315fa8b2,0x32dd31ed,0xb3feabc6,0x326dad64,0xad64326d,
  0x30c431ed,0xaed7b2dd,0x2bc63388,0xa248b3ea,0x2bc631ed,0x315fb3c3,0xb3ea2d64,0x2ed730c4,0xa8b231ed,0x3388b01d,0x301db388,0xb1ed28b2,
  0xb01d31ed,0x22482bc6,0x30c4ad64,0x3388b26d,0x33ea33fe,0x338833c3,0x32dd333b,0x31ed326d,0xb2ddb3fe,0xa248b01d,0x326d2ed7,0x338833ea,
  0x30c433fe,0xb33babc6,0xabc6b33b,0x33fe30c4,0xabc6b3fe,0x31ed32dd,0xb3eaaed7,0x333ba8b2,0xa8b233fe,0x2d64b3c3,0xb01d333b,0x315fb26d,
  0x301db3fe,0xb3fe301d,0x30c42ed7,0x2d64b3ea,0xb26d33fe,0x2ed72bc6,0x33c3b33b,0xa248b0c4,0x33c3b3fe,0x315fb2dd,0x28b2aed7,0xaed728b2,
  0xb0c4315f,0xaed7301d,0xabc62d64,0xa24828b2,0xabc6315f,0x315fabc6,0x33eab388,0x2ed7b26d,0x28b2315f,0x3388b2dd,0xb01dad64,0xb1ed33ea,
  0x301d315f,0x2248b3c3,0xb0c43388,0x3388b0c4,0x326d315f,0xb33bb01d,0x33c32d64,0xb3fea8b2,0x33c3315f,0xb1ed2bc6,0xa8b2b388,0x333b326d,
  0x33ea315f,0x2d6432dd,0xb2ddad64,0xb15fb3ea,0x32dd315f,0x33fe33c3,0x326d3388,0x2d6430c4,0x28b2a248,0x2d64abc6,0x301daed7,0x315fb0c4,
  0xb01d2248,0xb3fe32dd,0xb0c4333b,0x2d6428b2,0x326da248,0x2ed7b3c3,0xb3c32ed7,0xa248326d,0xb3c32248,0x315f301d,0xa8b2b33b,0xaed733ea,
  0x33eaa248,0xb3882bc6,0x32ddaed7,0xb1ed30c4,0xb2dd2248,0x2248b2dd,0x326d333b,0xb388a8b2,0x30c4a248,0x333b33c3,0xabc62ed7,0xb3feb26d,
  0xabc62248,0xb1edb01d,0xb3eab33b,0xb33bb3ea,0xb26d31ed,0xb33b32dd,0xb3c33388,0xb3fe33ea,0xb3c331ed,0xb1ed33c3,0x28b22d64,0x333bb0c4,
  0xb3ea31ed,0x2d64301d,0x32ddb388,0xb15fa8b2,0xb2dd31ed,0x33feabc6,0xb26dad64,0x2d64326d,0xb0c431ed,0x2ed7b2dd,0xabc63388,0x2248b3ea,
  0xabc631ed,0xb15fb3c3,0x33ea2d64,0xaed730c4,0x28b231ed,0xb388b01d,0xb01db388,0x31ed28b2,0x301d31ed,0xa2482bc6,0xb0c4ad64,0xb388b26d,
  0xb3ea33fe,0xb38833c3,0xb2dd333b,0xb1ed326d,0x32ddb3fe,0x2248b01d,0xb26d2ed7,0xb38833ea,0xb0c433fe,0x333babc6,0x2bc6b33b,0xb3fe30c4,
  0x2bc6b3fe,0xb1ed32dd,0x33eaaed7,0xb33ba8b2,0x28b233fe,0xad64b3c3,0x301d333b,0xb15fb26d,0xb01db3fe,0x33fe301d,0xb0c42ed7,0xad64b3ea,
  0x326d33fe,0xaed72bc6,0xb3c3b33b,0x2248b0c4,0xb3c3b3fe,0xb15fb2dd,0xa8b2aed7,0x2ed728b2,0x29ed29ed,0x29ed29ed,0x29ed29ed,0x29ed29ed,
  0x2bc32a6d,0x2add2bea,0x23c628c4,0xa81da0b2,0x2bc32add,0xa3c6281d,0xabc3aadd,0x23c6a81d,0x29ed2b3b,0xabfea564,0x295fa6d7,0x1a482b88,
  0x25642b88,0xa564ab88,0x25642b88,0xa564ab88,0xa0b22bc3,0x2a6daadd,0xabea23c6,0x28c4281d,0xa8c42bea,0x2a6da0b2,0x28c4abea,0xaa6d20b2,
  0xab3b2bfe,0xa564295f,0x26d79a48,0x2b88a9ed,0x29ed29ed,0x29ed29ed,0x29ed29ed,0x29ed29ed,0xabc3aa6d,0xaaddabea,0xa3c6a8c4,0x281d20b2,
  0x2bc32add,0xa3c6281d,0xabc3aadd,0x23c6a81d,0xa9edab3b,0x2bfe2564,0xa95f26d7,0x9a48ab88,0x25642b88,0xa564ab88,0x25642b88,0xa564ab88,
  0x20b2abc3,0xaa6d2add,0x2beaa3c6,0xa8c4a81d,0xa8c42bea,0x2a6da0b2,0x28c4abea,0xaa6d20b2,0x2b3babfe,0x2564a95f,0xa6d71a48,0xab8829ed,
  0x295f295f,0x295f295f,0x295f295f,0x295f295f,0x23c628c4,0xa81da0b2,0xabc3aa6d,0xaaddabea,0xa3c6281d,0xabc3aadd,0x23c6a81d,0x2bc32add,
  0xa95f26d7,0x9a48ab88,0x29ed2b3b,0xabfea564,0xab882564,0x2b88a564,0xab882564,0x2b88a564,0xabea23c6,0x28c4281d,0x20b2abc3,0xaa6d2add,
  0xaa6d20b2,0xa8c42bea,0x2a6da0b2,0x28c4abea,0xa6d71a48,0xab8829ed,0xab3b2bfe,0xa564295f,0x295f295f,0x295f295f,0x295f295f,0x295f295f,
  0xa3c6a8c4,0x281d20b2,0x2bc32a6d,0x2add2bea,0xa3c6281d,0xabc3aadd,0x23c6a81d,0x2bc32add,0x295fa6d7,0x1a482b88,0xa9edab3b,0x2bfe2564,
  0xab882564,0x2b88a564,0xab882564,0x2b88a564,0x2beaa3c6,0xa8c4a81d,0xa0b22bc3,0x2a6daadd,0xaa6d20b2,0xa8c42bea,0x2a6da0b2,0x28c4abea,
  0x26d79a48,0x2b88a9ed,0x2b3babfe,0x2564a95f,0xabfe2bfe,0xabfe2bfe,0xabfe2bfe,0xabfe2bfe,0xaadd2bea,0xa3c628c4,0x281da0b2,0x2bc3aa6d,
  0xa81d2bc3,0x2adda3c6,0x281dabc3,0xaadd23c6,0x9a482b88,0x29edab3b,0xabfe2564,0x295f26d7,0x26d72b3b,0xa6d7ab3b,0x26d72b3b,0xa6d7ab3b,
  0x2a6d2add,0xabeaa3c6,0x28c4a81d,0x20b22bc3,0x2bea2a6d,0xa0b228c4,0xabeaaa6d,0x20b2a8c4,0x2b8829ed,0x2b3b2bfe,0x2564295f,0xa6d79a48,
  0xabfe2bfe,0xabfe2bfe,0xabfe2bfe,0xabfe2bfe,0x2addabea,0x23c6a8c4,0xa81d20b2,0xabc32a6d,0xa81d2bc3,0x2adda3c6,0x281dabc3,0xaadd23c6,
  0x1a48ab88,0xa9ed2b3b,0x2bfea564,0xa95fa6d7,0x26d72b3b,0xa6d7ab3b,0x26d72b3b,0xa6d7ab3b,0xaa6daadd,0x2bea23c6,0xa8c4281d,0xa0b2abc3,
  0x2bea2a6d,0xa0b228c4,0xabeaaa6d,0x20b2a8c4,0xab88a9ed,0xab3babfe,0xa564a95f,0x26d71a48,0x1a489a48,0x1a489a48,0x1a489a48,0x1a489a48,
  0x281da0b2,0x2bc3aa6d,0x2addabea,0x23c6a8c4,0x2adda3c6,0x281dabc3,0xaadd23c6,0xa81d2bc3,0x2bfea564,0xa95fa6d7,0x9a482b88,0x29edab3b,
  0x2b3ba6d7,0xab3b26d7,0x2b3ba6d7,0xab3b26d7,0x28c4a81d,0x20b22bc3,0xaa6daadd,0x2bea23c6,0x20b2a8c4,0x2bea2a6d,0xa0b228c4,0xabeaaa6d,
  0xa564a95f,0x26d71a48,0x2b8829ed,0x2b3b2bfe,0x1a489a48,0x1a489a48,0x1a489a48,0x1a489a48,0xa81d20b2,0xabc32a6d,0xaadd2bea,0xa3c628c4,
  0x2adda3c6,0x281dabc3,0xaadd23c6,0xa81d2bc3,0xabfe2564,0x295f26d7,0x1a48ab88,0xa9ed2b3b,0x2b3ba6d7,0xab3b26d7,0x2b3ba6d7,0xab3b26d7,
  0xa8c4281d,0xa0b2abc3,0x2a6d2add,0xabeaa3c6,0x20b2a8c4,0x2bea2a6d,0xa0b228c4,0xabeaaa6d,0x2564295f,0xa6d79a48,0xab88a9ed,0xab3babfe,
  0xa95fa95f,0xa95fa95f,0xa95fa95f,0xa95fa95f,0xa3c6a8c4,0x281d20b2,0x2bc32a6d,0x2add2bea,0x23c6a81d,0x2bc32add,0xa3c6281d,0xabc3aadd,
  0x295fa6d7,0x1a482b88,0xa9edab3b,0x2bfe2564,0x2b88a564,0xab882564,0x2b88a564,0xab882564,0x2beaa3c6,0xa8c4a81d,0xa0b22bc3,0x2a6daadd,
  0x2a6da0b2,0x28c4abea,0xaa6d20b2,0xa8c42bea,0x26d79a48,0x2b88a9ed,0x2b3babfe,0x2564a95f,0xa95fa95f,0xa95fa95f,0xa95fa95f,0xa95fa95f,
  0x23c628c4,0xa81da0b2,0xabc3aa6d,0xaaddabea,0x23c6a81d,0x2bc32add,0xa3c6281d,0xabc3aadd,0xa95f26d7,0x9a48ab88,0x29ed2b3b,0xabfea564,
  0x2b88a564,0xab882564,0x2b88a564,0xab882564,0xabea23c6,0x28c4281d,0x20b2abc3,0xaa6d2add,0x2a6da0b2,0x28c4abea,0xaa6d20b2,0xa8c42bea,
  0xa6d71a48,0xab8829ed,0xab3b2bfe,0xa564295f,0x29ed29ed,0x29ed29ed,0x29ed29ed,0x29ed29ed,0x2bc32a6d,0x2add2bea,0x23c628c4,0xa81da0b2,
  0x2bc32add,0xa3c6281d,0xabc3aadd,0x23c6a81d,0x29ed2b3b,0xabfea564,0x295fa6d7,0x1a482b88,0x25642b88,0xa564ab88,0x25642b88,0xa564ab88,
  0xa0b22bc3,0x2a6daadd,0xabea23c6,0x28c4281d,0xa8c42bea,0x2a6da0b2,0x28c4abea,0xaa6d20b2,0xab3b2bfe,0xa564295f,0x26d79a48,0x2b88a9ed,
  0x29ed29ed,0x29ed29ed,0x29ed29ed,0x29ed29ed,0xabc3aa6d,0xaaddabea,0xa3c6a8c4,0x281d20b2,0x2bc32add,0xa3c6281d,0xabc3aadd,0x23c6a81d,
  0xa9edab3b,0x2bfe2564,0xa95f26d7,0x9a48ab88,0x25642b88,0xa564ab88,0x25642b88,0xa564ab88,0x20b2abc3,0xaa6d2add,0x2beaa3c6,0xa8c4a81d,
  0xa8c42bea,0x2a6da0b2,0x28c4abea,0xaa6d20b2,0x2b3babfe,0x2564a95f,0xa6d71a48,0xab8829ed,0x9a481a48,0x9a481a48,0x9a481a48,0x9a481a48,
  0xa81d20b2,0xabc32a6d,0xaadd2bea,0xa3c628c4,0xaadd23c6,0xa81d2bc3,0x2adda3c6,0x281dabc3,0xabfe2564,0x295f26d7,0x1a48ab88,0xa9ed2b3b,
  0xab3b26d7,0x2b3ba6d7,0xab3b26d7,0x2b3ba6d7,0xa8c4281d,0xa0b2abc3,0x2a6d2add,0xabeaa3c6,0xa0b228c4,0xabeaaa6d,0x20b2a8c4,0x2bea2a6d,
  0x2564295f,0xa6d79a48,0xab88a9ed,0xab3babfe,0x9a481a48,0x9a481a48,0x9a481a48,0x9a481a48,0x281da0b2,0x2bc3aa6d,0x2addabea,0x23c6a8c4,
  0xaadd23c6,0xa81d2bc3,0x2adda3c6,0x281dabc3,0x2bfea564,0xa95fa6d7,0x9a482b88,0x29edab3b,0xab3b26d7,0x2b3ba6d7,0xab3b26d7,0x2b3ba6d7,
  0x28c4a81d,0x20b22bc3,0xaa6daadd,0x2bea23c6,0xa0b228c4,0xabeaaa6d,0x20b2a8c4,0x2bea2a6d,0xa564a95f,0x26d71a48,0x2b8829ed,0x2b3b2bfe,
  0xabfe2bfe,0xabfe2bfe,0xabfe2bfe,0xabfe2bfe,0xaadd2bea,0xa3c628c4,0x281da0b2,0x2bc3aa6d,0xa81d2bc3,0x2adda3c6,0x281dabc3,0xaadd23c6,
  0x9a482b88,0x29edab3b,0xabfe2564,0x295f26d7,0x26d72b3b,0xa6d7ab3b,0x26d72b3b,0xa6d7ab3b,0x2a6d2add,0xabeaa3c6,0x28c4a81d,0x20b22bc3,
  0x2bea2a6d,0xa0b228c4,0xabeaaa6d,0x20b2a8c4,0x2b8829ed,0x2b3b2bfe,0x2564295f,0xa6d79a48,0xabfe2bfe,0xabfe2bfe,0xabfe2bfe,0xabfe2bfe,
  0x2addabea,0x23c6a8c4,0xa81d20b2,0xabc32a6d,0xa81d2bc3,0x2adda3c6,0x281dabc3,0xaadd23c6,0x1a48ab88,0xa9ed2b3b,0x2bfea564,0xa95fa6d7,
  0x26d72b3b,0xa6d7ab3b,0x26d72b3b,0xa6d7ab3b,0xaa6daadd,0x2bea23c6,0xa8c4281d,0xa0b2abc3,0x2bea2a6d,0xa0b228c4,0xabeaaa6d,0x20b2a8c4,
  0xab88a9ed,0xab3babfe,0xa564a95f,0x26d71a48,0x3bfb3bff,0x3be53bf2,0x3bbf3bd4,0x3b873ba5,0x3bd03bfb,0x3b013b7c,0x399d3a60,0x378538bc,
  0x35173b52,0xbbc9b7c8,0xb074ba9b,0x3bfe391b,0x319e3b27,0xbbf3b979,0x363cb80a,0x3a2d3bc5,0xba093986,0x3a7eb8f8,0xbae5385f,0x3b3db77a,
  0xbabd393c,0x3bb0b699,0xbc00305b,0x3ba730d7,0xbb2a35c8,0xb8353bb2,0x3a64b1e8,0x3962bbf7,0xba90350b,0xba413bff,0x3602340e,0x3bf6bad8,
  0xac6aa5e4,0xb122af59,0xb402b294,0xb56ab4b7,0xb2deac9c,0xb7bdb5a5,0xb9b3b8d6,0xbb10ba73,0xbb96b676,0xb359bafe,0x3bec3884,0x2a163a29,
  0xbbe0b72c,0x2f27b9d6,0x3b5e3ae8,0xb91633a2,0xb941b9c9,0x38ad3a45,0xb80fbab3,0x36d23b13,0xb850ba0d,0x346f3b4a,0x1fdbbbed,0xb4ab3be8,
  0x3721bb76,0xbace3463,0xb8d13bdd,0x39ebadfb,0x3894bb98,0xb8fd281f,0xbb6a3bbd,0x2e2d3825,0x3b3f3b65,0x3ae83b16,0x3a813ab6,0x3a0d3a49,
  0x3263356a,0xad972b43,0xb5dfb359,0xb8eeb7f3,0xa9b139aa,0xbbedba25,0x3340b889,0x3b983afb,0xbaa2aa16,0xb4cfbb8e,0x3c0038ad,0xb44b38e5,
  0xbb853625,0x3bbdb4c3,0xbbe432ad,0x3bfbaf8b,0xbaacb6d2,0x39243954,0xb65fbace,0x2fbd3bb8,0xb9661648,0xba603bf8,0x383a31cf,0x3b27bbb3,
  0x3219b9eb,0xbb1836f4,0xb9903be5,0x37dd3010,0xb6c6b61a,0xb80ab76f,0xb8a8b85a,0xb93cb8f3,0xbbd7bb87,0xbbf8bbfd,0xbb71bbc9,0xba4dbaf1,
  0xbbfeb9a6,0x305bb91f,0x3bcb3a97,0xb50b37d2,0xb87abbfe,0x3ba13546,0x24523a7e,0xbbb5ba54,0xb576bb63,0x340e3ba3,0xb13bbbd3,0x2c9c3bf2,
  0x386abb3d,0xba2139f8,0x3b57b835,0xbbf13432,0x39e7bc00,0xb8d6adc9,0xbacb3bde,0x372c3457,0x3bdab962,0x3764bb35,0xb9c03122,0xbaf73bef,
  0x398b39cd,0x38fd3946,0x386538b2,0x37853815,0xba85b9c9,0xbb92bb1e,0xbbfebbdd,0xbbc2bbf5,0xb66b3682,0xbb01bb94,0x387fb371,0x3a2d3beb,
  0xbac7bb76,0x3a00ad33,0x36bb3bd4,0xbbeab79b,0xbc0026ad,0x3bf32c38,0xbbd6b109,0x3ba733eb,0x3153bbff,0xb70a3b9e,0x396bba9b,0xbade390c,
  0xb5d4b5bc,0xbbb03b2c,0x32013830,0x3bf6ba67,0x3bccbb52,0x2c06b92e,0xbb83385f,0xb8c73bab,0xb9c5b982,0xba41ba04,0xbab0ba7a,0xbb10bae1,
  0xb8a3b986,0xb52fb74e,0xa94db1e8,0x33d32e91,0xbb54bb4f,0x37bdb523,0x3a9e3bc8,0xb916308d,0x3840b5c8,0x394a3bf9,0xbb42b294,0xb0a6bb0a,
  0x251bbbff,0xaf273bfc,0x327cbbe6,0xb4ab3bc0,0x3be325e4,0xbb2fb4e7,0x39e33884,0xb81aba35,0x3b73bb78,0xb46fb715,0xbbdc3ad1,0x2e2d38cc,
  0x33283676,0x3bfcba19,0x3581bab3,0xba6b3493,0x363136dd,0x34cf3581,0x32c6341a,0x2fbd3153,0xbae1bb65,0xb970ba39,0xb715b889,0xb16cb4f3,
  0xb9a12a7a,0xb924bbfe,0x3a933042,0x37dd3bcc,0x308db9aa,0x3b453b07,0xb94632ad,0xb845bbfa,0xbb68b55e,0x3b1836bb,0xbabab805,0x3a4d38a3,
  0x3bc0b625,0xbbfe2ec3,0x3b9431cf,0xba89b742,0x9cb6b95d,0xbbf8396b,0xb1b63a5c,0x3bb5b840,0x38cc9648,0x3b81bbac,0xac38b85a,0xbbce3933,
  0xbb60bb3a,0xbba1bb83,0xbbd2bbbc,0xbbf1bbe3,0x3815361a,0x39df3907,0x3b2c3a97,0x3be23b9c,0xb9afbbfd,0x3a21294d,0x388e3bee,0xbaf7b328,
  0x3beb39a6,0xb6af37a6,0xba04bbd3,0x3ac42d00,0x360ebb89,0xb7643b42,0x3855baeb,0xb8ee3a85,0x33eb3b63,0x28e8bbf5,0xb5233bde,0x389ebb21,
  0x3c00b9f0,0x2d97b9e3,0xbbdf38db,0xb44b3ac7,0xba673c00,0x358d3487,0x3bfcbab6,0x330fba15,0x3b7a3bf1,0x394a3a93,0x33893764,0xb3d39cb6,
  0x3afb3be2,0x35eb3946,0xb4c328e8,0xbaa9b8cc,0x27763af7,0xbb2fbaba,0x3a76ad97,0x30a63b60,0xaf8b3ac4,0xb994bb94,0x3bf8358d,0xb8743815,
  0xbb4c38ee,0x3bfcb1b6,0xbad5b4cf,0x381a39af,0xbbb3389e,0x3b592c38,0xb76fb970,0xb24b3beb,0xb9d2344b,0xbb923bd2,0xb0f03924,0x3a6bb60e,
  0xb8f3330f,0xbc003b2c,0xb91f3b45,0x323233eb,0xb5b1afbd,0xba00b88e,0xbbc6bb18,0xbbc2bc00,0xb7d2b16c,0xbb6fba04,0xbba3bbfe,0xb86fba67,
  0xbbffb7dd,0x370ab855,0x38b73bf8,0xbbeab631,0xbbf2b845,0x39bcb523,0x2dc93b81,0xbaa5bae1,0xb68dba4d,0xac063bdf,0x382abba1,0xbade39a1,
  0xb457ba89,0xb6543bfc,0x3b16b9df,0xbbd8308d,0x397dbbb5,0xb52fb2c6,0xbbe73a21,0xb8c73b68,0x3a49bbce,0x2311b715,0xba2536af,0xbbd93bc0,
  0xb958b785,0xbb81ba9e,0xbbefbbf3,0xba89bb73,0xbbf7bbc2,0xb9b8bb42,0xaf59b70a,0x384a3328,0xbb8bba2d,0x39dfb27c,0x34263bb0,0xbbceb98b,
  0xb4b7bbea,0x3b6c39e3,0xbafe2c06,0x3185ba85,0xaadebba7,0xb6af3bdc,0x3a58ba41,0xbbe2366b,0x3a29bade,0xbc003581,0x3a45352f,0xb2f7bac7,
  0x3b37bbf6,0x28e8b865,0xbaee37bd,0xbac43c00,0x3b13b8c7,0x3b5cbbfe,0x3463b94a,0xb8993153,0xb9f4bb10,0xb58db87f,0x3029af27,0x389e35d4,
  0x2dfbb3d3,0x399936bb,0x3bf23b2f,0x3ac13bcc,0x3552b916,0x39703bd6,0xbbbab46f,0x330fb9c5,0x3ba530a6,0xb5f7396b,0xb7c8bbfc,0x3be138a3,
  0x3bfdb4ab,0xbb45b201,0x38e038fd,0xb16cbb54,0x391b381a,0xa17fbb83,0xb8f83b92,0x3bcfb840,0x36e82e2d,0x3bfebab0,0x37febb01,0xb845251b,
  0xb77a3a6b,0x3648294d,0x3bb2ba00,0x3a8cbbe3,0xb742b93c,0x2311b340,0x37a6340e,0x3aa93966,0x3b963a4d,0x3b7f3c00,0x380f3a21,0xb0be3219,
  0x3933b50b,0x35eb3be4,0xbbf5b8d6,0x3874b6c6,0x39413bb5,0xbbffb65f,0x38d1b764,0x33ba3bd7,0x3b9c2c9c,0xb994b83a,0x34873ae8,0x324bbbfe,
  0xb7213bf1,0x3b47b990,0xbbbf2d97,0x38c1387a,0x2d00372c,0x3b59b8a8,0x3a39bbed,0xb232b576,0xbbfb3af7,0xb9743b71,0x307434cf,0x3adbb86a,
  0x3b213a0d,0x3c003bcb,0x3b073bbd,0x386f39e7,0x351738ee,0xb599a452,0xbae5b924,0xbbe9bbda,0x3a153b98,0xbb6fb13b,0x2ec3ba60,0x3aa53b3f,
  0xba09344b,0xa884bb57,0x3a643b18,0xbbc3b263,0xb4f33bfb,0x39bcbacb,0xbbac380a,0x3bd8a9b1,0xbb2aafbd,0x36a439c0,0x3402bbf8,0xba6f3aa2,
  0xbbfa3b27,0xb6543a81,0x3907b05b,0x3bd9bb85,0x2c6ab7dd,0xb9da35df,0xbbec3ba1,0xb8203aac,0x3bf53b87,0x3b6c3bec,0x392e3a7e,0x32f73721,
  0xb9e7b785,0xbbfcbb5e,0xba81bbb0,0xb43eb894,0x379b3bfe,0xbc00b80f,0x374eb835,0x38993bfb,0xbb3fba2d,0x3b329fdb,0xb3403a41,0xb8eabbd0,
  0xb90c3b3d,0x3b5cb8d1,0xbbf93122,0x3ac13517,0x29b1bba7,0xb94f3b6a,0x3be4b7bd,0xbaf4b19e,0xbbab3962,0xb9993bbf,0x34e73359,0x3be1ba09,
  0x3b85bbf6,0x353ab99d,0xb83a2f27,0xbbf03abd,0x2e91356a,0xb5f7b074,0xba19b8ad,0xbbcfbb2a,0xb966bb10,0xaba7b63c,0x38a8346f,0x3bb73a90,
  0xbb0aaa16,0xa17fbae5,0x3b1e3ace,0xba8c2c6a,0x36c6b916,0x36ff3c00,0xbbcbb8fd,0x3a50b2de,0xba35b6d2,0x36483a64,0x2d33bbe5,0xb84a3b96,
  0x3bfeb4ab,0xb9fcb602,0x313b3b01,0x37e8bbe0,0x3493b9eb,0xb9b83402,0xbb9e3bc9,0xb1853941,0x35762e2d,0x3b90b9b3,0x3acbbbf3,0x2fefb850,
  0x3a543bcf,0x2884374e,0xb9f8b648,0xbbe9bbab,0x398b3bb7,0xb4db3340,0xbbdcb9fc,0xb911bb85,0xb4323a8c,0xb6a4bbf9,0x3b3539b8,0xbbc3ae91,
  0xb66b3a50,0xad65bbe4,0x38653b90,0xbb0db966,0xbbef384a,0x39da34e7,0x2b43bb6c,0xba6f3b0a,0xbc0037e8,0x3759383a,0x387fbbfc,0xbbf636c6,
  0xb7f33185,0xbb7f3a19,0xbb8e3c00,0xb8203a35,0xb5d42fef,0xba1d38a8,0xbbd63b32,0xbba93bfe,0xb8e5b2f7,0xbbffbb1e,0xb954bb5c,0x30beb493,
  0xb9c5b43e,0xbb9fbbcb,0xb201b94f,0x3a313576,0xbbb8b899,0x3b47ad33,0xb6f43999,0xb3babbf5,0xbb54b8ea,0x3bf9313b,0xbab0353a,0x3790b9e7,
  0xb010bac1,0xb9743b9e,0x3bfdb5f7,0xb8c1b79b,0x251bbaf4,0xbb1b3acb,0x3a9e2ba7,0x2e5fbb3f,0x3af1bbe1,0x3599b92e,0xb546a17f,0xbadb390c,
  0x3b73bbf0,0x3929ba81,0x327cb6ff,0xb49f29b1,0xb825baa9,0x353aaec3,0x3b7c3994,0x3af43bfa,0x360eb0be,0x3bf43a64,0x388e3b47,0xb7372c6a,
  0x38bcb874,0x2ba73bac,0xb979bb59,0x3bf03742,0x3c0033ba,0xbb043402,0x3855b974,0xacce3b96,0x3bc5b24b,0xb6ffb907,0xb6993c00,0x3bb7b933,
  0x363138c1,0x3902bbec,0xbbdf3599,0x34ff3941,0x30d73232,0x39fcb7a6,0x3bffbb6f,0x3a50bb9c,0xb9a13adb,0xb47b380f,0x32c62884,0x3937b721,
  0x3ad8386f,0x3b903bf5,0x35a539bc,0xb7e8ad00,0x3b683be9,0x2ef538d1,0xba93b6a4,0xbb24bbfb,0x3a733aa5,0xbbfcb487,0x39d6b654,0xafef3b21,
  0x1cb63bc3,0xb7b2bbbf,0x3aba39da,0xbbfab517,0xb3a23bd8,0x3b32ba39,0xbb4a2311,0x343e3a15,0xbb603a6f,0x3a3d3074,0x31b6bb7f,0xbb9a3a09,
  0xbbe83bd9,0xb94f3b07,0xa81f35eb,0x38eab4f3,0xb9af3820,0xbbae3ae5,0xbbd23bff,0xba113b2a,0x319e389e,0xb929b426,0xbc00bb45,0xb911bb37,
  0xbbffbac1,0xb805bafe,0x382a217f,0x3bfd3b13,0xbabd330f,0x34dbba58,0x36023bfe,0xbb0db9f4,0xb68dbbe1,0x3a5c3a45,0xbbe7b648,0x3b89adfb,
  0xba90b16c,0x2d653aee,0x39b3bb81,0xbbf63552,0x397dbbcf,0xbbbc3463,0x338939b8,0x39f0bba5,0x32deb845,0xb7593029,0xbb5e39df,0xbba93bfd,
  0x3b7aba8c,0x3beebbf2,0x3a76bb6c,0x36ddb91b,0xbbe0ba89,0xba1dbbba,0x1fdbb6af,0x3a3136e8,0xa776b84a,0x3aeb37c8,0x3ad53c00,0xaa7a377a,
  0xb850bbce,0x3b9f38e0,0xbb6a28e8,0x3790b958,0x3b4cb185,0xb8db38f8,0x30f0bb5c,0x355e3bf7,0x3894bbe2,0xbbf937fe,0x399d358d,0x2e5fbb8b,
  0x39d232f7,0x341abbb2,0xbbc63999,0x395d34b7,0x3bd0bac4,0x3b1bbbef,0x363cb970,0xb49faade,0xb5b13899,0x30422f59,0x38b7b5f7,0x3b3aba29,
  0x3219b3d3,0x3b0438b7,0x3b713bfc,0x34ff397d,0x36e83aa9,0xb8b2adc9,0xbbefbb59,0xb5bcba49,0x3bd730a6,0xb902382a,0xa452bb92,0x39373b7a,
  0xb9583874,0x3371bb16,0x34263c00,0xb982bafb,0x387a381a,0x347bbbe7,0xbb573a00,0x3b242776,0xbb8b324b,0x31093a25,0x3a58bb6f,0xbb4f2f8b,
  0xb86a3a6b,0x2ef53389,0x39c0b70a,0x3bfabb4c,0xaadeb232,0xb83034c3,0xbaee39bc,0xbbff3bb3,0x3bda3bc2,0x37b23a76,0xb5df2c06,0xbb9ab9d2,
  0xbb37b86f,0xba7abbf8,0x3029b654,0x3b7838f3,0x32633bea,0xba3dbad5,0x3c00352f,0xba1135b1,0xb9f4baa5,0x3bc8376f,0xbbba2311,0x39cdb7d2,
  0xbaa23ade,0x3baeb0f0,0xb65fb94a,0xb7373bff,0x3552bbd8,0xbbe6391f,0x38e035eb,0x3682bbf2,0xbaac38c7,0xbbf43bc6,0xb9903b2f,0xacce368d,
  0x3bfdbbd9,0x3ad1bba3,0x37feb994,0x26adb457,0x38a33b9a,0xb8dba452,0xbb83bbae,0x2a7ab86a,0x37423b78,0xbab6b426,0xb907bbe6,0x39aa2ade,
  0xb8403a11,0x341abb57,0x294d3bf4,0xb55ebbda,0xb93339cd,0x3889ba58,0xb7a63ad1,0x3625bb37,0xbbe33737,0x304239c0,0x3b42bb04,0xb95db263,
  0xbb9c3682,0xb2ad3aee,0x3bf5b8b2,0x1648b9f4,0xb3282cce,0xb80535df,0xb9e33902,0xbb3a3aa2,0xad0026ad,0xb1cf3029,0xb4873371,0xb61a3552,
  0xba85b4ff,0xba5cbc00,0x3581b47b,0x3bfd3aac,0xbb21b5bc,0xb85abbba,0x3a393109,0x39a63bfd,0xbac7b937,0x3bbc365f,0xbbfeaef5,0x3b89b219,
  0xba15b982,0x3a9738e0,0xbb07b830,0x3b6336e8,0x3153bb24,0xbbee3990,0x36bb37b2,0x39f0bbd7,0x34f3bb4f,0xbbd337fe,0xaec33a7a,0x3c00b958,
  0x3bccbbfa,0x3aebbb71,0x396bba3d,0x36ddb87a,0x3bfabbff,0x3bdebbef,0x3bacbbc8,0x3b65bb8b,0x3bc03911,0x38303b6a,0xb946ad65,0xbb4fbbd0,
  0x3a353bfd,0xb85f30f0,0xbb1ebbbc,0x35c8b5b1,0x38cc3b0d,0xba7ab99d,0x3b943759,0xbbffb19e,0xb4933b89,0x31e8bbc6,0xad333bee,0xa5e4bbff,
  0xb8153bf6,0x3bc8b63c,0xac38ba1d,0xbb783abd,0xbbf539f0,0x329438b7,0x3b9ebaeb,0xb676b68d,0xbbeb3ba9,0xbbe63c00,0xbb2c3b9f,0xb9cd3a90,
  0xb79b36dd,0xb884382a,0xb92e38db,0xb9c9397d,0x33eb3a31,0xbad1b602,0xba04bbf9,0x3682b2de,0xb90c2a7a,0xbab3bbe7,0x374eb41a,0x3b763b7a,
  0xba673790,0x38b2b9b3,0xb5233b1b,0x26adbbe0,0xbbabb55e,0x3bdd3389,0xbbf9b042,0x3bff2776,0xbae12e5f,0xb3713b5e,0x3bfcb929,0xb5bcb850,
  0xae91b95d,0xbbd43a76,0x34e73805,0x3b52bb4c,0x308db49f,0xb1091fdb,0xb71534db,0xb9823894,0x3b0abb3a,0x3a9bbad5,0x3a19ba5c,0x3986b9d2,
  0x2f8bb7e8,0x3bde3979,0x376f3b32,0xb9aab0d7,0x3bb83b24,0xb1223855,0xbbfdba3d,0xaa16b9a1,0x3bb3afef,0xbab63699,0x391fb94f,0xb6253ad8,
  0x30103bfa,0xb359bbdf,0x35463bae,0xb6d2bb68,0x38f3343e,0x3889bbff,0xbba3353a,0x96483a73,0xbaf13b9a,0x38ad32c6,0x39f8bbf4,0xb9eb9cb6,
  0xb7d238ea,0xb2ad35a5,0x2dc92ba7,0x361ab3a2,0xba543a11,0xbace3a93,0xbb353b04,0xbb873b60,0x3bf23af4,0x31cf39d6,0xbb16b6ff,0xb9a6bbe8,
  0xb4323737,0xbbe5baba,0x2b43b902,0x3bfe39af,0x34573bf0,0xb85abb4a,0x3a2539fc,0xbb63b825,0xbbef2cce,0x3bc9b1b6,0xbb8e347b,0x3b3db60e,
  0xba493bb7,0x3a97a81f,0x34c3bb90,0xbc0038bc,0xb7f3b4ff,0xba7e3bd2,0x39542ef5,0x3962bc00,0xbafb3a50,0xbbd33b7c,0xbbf83bfc,0xbb653bc5,
  0x38e5b937,0x3835b88e,0x36f4b7b2,0x356ab631,0xbb13bbe9,0x31e8b6f4,0x3bf239da,0x36763af1,0x3be83911,0x340e3ab0,0xbb7cb759,0xb72cbb73,
  0x2dfbbbc3,0x32943bfd,0xb7c8bb7f,0x39c93a54,0x38253b0d,0xb8d6ba9e,0x39793a1d,0xba0db98b,0x3ba5ba6f,0xb884b546,0xb8f83bff,0x3b76b432,
  0xb8bc3bf6,0x3ae8b27c,0x3699bb9f,0xbb98366b,0x391bb820,0x3ab3b9f8,0x3bb2bb47,0x3bffbbef,0xbbc53ba9,0xbbed3bdc,0xbbff3bf9,0xbbfb3c00,
  0x377ab0be,0x3bdd3b35,0x2f593974,0xbb52b7f3,0x30d73a31,0xbbbdb865,0xb5a5bb1b,0x3b2735d4,0x3bf733ba,0xbbd42b43,0x3afeb599,0xb98638e5,
  0xbad83790,0x3a60b87f,0xb9d63929,0x393cb9c5,0x34b738c1,0x3a9bbb8e,0xba45a884,0xb5c83bb8,0xba732e5f,0xb80a3bd6,0x3b4ab4db,0x350bbb54,
  0xba293adb,0xb85f3954,0xb46336a4,0x25e43010,0x33a2b49f,0x305bb201,0x281fad65,0xac9c251b,0x3f803f80,0x3f803f80,0x3f803f80,0x3f803f80,
  0x3f803f80,0x3f803f80,0x3f803f80,0x3f803f80,0x3f803f80,0x3f803f80,0x3f803f80,0x3f803f80,0x3f803f80,0x3f803f80,0x3f803f80,0x3f803f80,
  0x3f803f80,0x3f803f80,0x3f803f80,0x3f803f80,0x3f803f80,0x3f803f80,0x3f803f80,0x3f803f80,0x3f803f80,0x3f803f80,0x3f803f80,0x3f803f80,
  0x3f803f80,0x3f803f80,0x3f803f80,0x3f803f80,0x3f803f80,0x3f803f80,0x3f803f80,0x3f803f80,0x3f803f80,0x3f803f80,0x3f803f80,0x3f803f80,
  0x3f803f80,0x3f803f80,0x3f803f80,0x3f803f80,0x3f803f80,0x3f803f80,0x3f803f80,0x3f803f80,0x3f803f80,0x3f803f80,0x3f803f80,0x3f803f80,
  0x3f803f80,0x3f803f80,0x3f803f80,0x3f803f80,0x3f803f80,0x3f803f80,0x3f803f80,0x3f803f80,0x3f803f80,0x3f803f80,0x3f803f80,0x3f803f80,
  0x3f803f80,0x3f803f80,0x3f803f80,0x3f803f80,0x3f803f80,0x3f803f80,0x3f803f80,0x3f803f80,0x3f803f80,0x3f803f80,0x3f803f80,0x3f803f80,
  0x3f803f80,0x3f803f80,0x3f803f80,0x3f803f80,0x3f803f80,0x3f803f80,0x3f803f80,0x3f803f80,0x3f803f80,0x3f803f80,0x3f803f80,0x3f803f80,
  0x3f803f80,0x3f803f80,0x3f803f80,0x3f803f80,0x3f803f80,0x3f803f80,0x3f803f80,0x3f803f80,0x3f803f80,0x3f803f80,0x3f803f80,0x3f803f80,
  0x3f803f80,0x3f803f80,0x3f803f80,0x3f803f80,0x3f803f80,0x3f803f80,0x3f803f80,0x3f803f80,0x3f803f80,0x3f803f80,0x3f803f80,0x3f803f80,
  0x3f803f80,0x3f803f80,0x3f803f80,0x3f803f80,0x3f803f80,0x3f803f80,0x3f803f80,0x3f803f80,0x3f803f80,0x3f803f80,0x3f803f80,0x3f803f80,
  0x3f803f80,0x3f803f80,0x3f803f80,0x3f803f80,0x3f803f80,0x3f803f80,0x3f803f80,0x3f803f80,0x3f803f80,0x3f803f80,0x3f803f80,0x3f803f80,
  0x3f803f80,0x3f803f80,0x3f803f80,0x3f803f80,0x3f803f80,0x3f803f80,0x3f803f80,0x3f803f80,0x3f803f80,0x3f803f80,0x3f803f80,0x3f803f80,
  0x3f803f80,0x3f803f80,0x3f803f80,0x3f803f80,0x3f803f80,0x3f803f80,0x3f803f80,0x3f803f80,0x3f803f80,0x3f803f80,0x3f803f80,0x3f803f80,
  0x3f803f80,0x3f803f80,0x3f803f80,0x3f803f80,0x3f803f80,0x3f803f80,0x3f803f80,0x3f803f80,0x3f803f80,0x3f803f80,0x3f803f80,0x3f803f80,
  0x3f803f80,0x3f803f80,0x3f803f80,0x3f803f80,0x3f803f80,0x3f803f80,0x3f803f80,0x3f803f80,0x3f803f80,0x3f803f80,0x3f803f80,0x3f803f80,
  0x3f803f80,0x3f803f80,0x3f803f80,0x3f803f80,0x3f803f80,0x3f803f80,0x3f803f80,0x3f803f80,0x3f803f80,0x3f803f80,0x3f803f80,0x3f803f80,
  0x3f803f80,0x3f803f80,0x3f803f80,0x3f803f80,0x3f803f80,0x3f803f80,0x3f803f80,0x3f803f80,0x3f803f80,0x3f803f80,0x3f803f80,0x3f803f80,
  0x3f803f80,0x3f803f80,0x3f803f80,0x3f803f80,0x3f803f80,0x3f803f80,0x3f803f80,0x3f803f80,0x3f803f80,0x3f803f80,0x3f803f80,0x3f803f80,
  0x3f803f80,0x3f803f80,0x3f803f80,0x3f803f80,0x3f803f80,0x3f803f80,0x3f803f80,0x3f803f80,0x3f803f80,0x3f803f80,0x3f803f80,0x3f803f80,
  0x3f803f80,0x3f803f80,0x3f803f80,0x3f803f80,0x3f803f80,0x3f803f80,0x3f803f80,0x3f803f80,0x3f803f80,0x3f803f80,0x3f803f80,0x3f803f80,
  0x3f803f80,0x3f803f80,0x3f803f80,0x3f803f80,0x3f803f80,0x3f803f80,0x3f803f80,0x3f803f80,0x3f803f80,0x3f803f80,0x3f803f80,0x3f803f80,
  0x3f803f80,0x3f803f80,0x3f803f80,0x3f803f80,0x3f803f80,0x3f803f80,0x3f803f80,0x3f803f80,0x3f803f80,0x3f803f80,0x3f803f80,0x3f803f80,
  0x3f803f80,0x3f803f80,0x3f803f80,0x3f803f80,0x3f803f80,0x3f803f80,0x3f803f80,0x3f803f80,0x3f803f80,0x3f803f80,0x3f803f80,0x3f803f80,
  0x3f803f80,0x3f803f80,0x3f803f80,0x3f803f80,0x3f803f80,0x3f803f80,0x3f803f80,0x3f803f80,0x3f803f80,0x3f803f80,0x3f803f80,0x3f803f80,
  0x3f803f80,0x3f803f80,0x3f803f80,0x3f803f80,0x3f803f80,0x3f803f80,0x3f803f80,0x3f803f80,0x3f803f80,0x3f803f80,0x3f803f80,0x3f803f80,
  0x3f803f80,0x3f803f80,0x3f803f80,0x3f803f80,0x3f803f80,0x3f803f80,0x3f803f80,0x3f803f80,0x3f803f80,0x3f803f80,0x3f803f80,0x3f803f80,
  0x3f803f80,0x3f803f80,0x3f803f80,0x3f803f80,0x3f803f80,0x3f803f80,0x3f803f80,0x3f803f80,0x3f803f80,0x3f803f80,0x3f803f80,0x3f803f80,
  0x3f803f80,0x3f803f80,0x3f803f80,0x3f803f80,0x3f803f80,0x3f803f80,0x3f803f80,0x3f803f80,0x3f803f80,0x3f803f80,0x3f803f80,0x3f803f80,
  0x3f803f80,0x3f803f80,0x3f803f80,0x3f803f80,0x3f803f80,0x3f803f80,0x3f803f80,0x3f803f80,0x3f803f80,0x3f803f80,0x3f803f80,0x3f803f80,
  0x3f803f80,0x3f803f80,0x3f803f80,0x3f803f80,0x3f803f80,0x3f803f80,0x3f803f80,0x3f803f80,0x3f803f80,0x3f803f80,0x3f803f80,0x3f803f80,
  0x3f803f80,0x3f803f80,0x3f803f80,0x3f803f80,0x3f803f80,0x3f803f80,0x3f803f80,0x3f803f80,0x3f803f80,0x3f803f80,0x3f803f80,0x3f803f80,
  0x3f803f80,0x3f803f80,0x3f803f80,0x3f803f80,0x3f803f80,0x3f803f80,0x3f803f80,0x3f803f80,0x3f803f80,0x3f803f80,0x3f803f80,0x3f803f80,
  0x3f803f80,0x3f803f80,0x3f803f80,0x3f803f80,0x3f803f80,0x3f803f80,0x3f803f80,0x3f803f80,0x3f803f80,0x3f803f80,0x3f803f80,0x3f803f80,
  0x3f803f80,0x3f803f80,0x3f803f80,0x3f803f80,0x3f803f80,0x3f803f80,0x3f803f80,0x3f803f80,0x3f803f80,0x3f803f80,0x3f803f80,0x3f803f80,
  0x3f803f80,0x3f803f80,0x3f803f80,0x3f803f80,0x3f803f80,0x3f803f80,0x3f803f80,0x3f803f80,0x3f803f80,0x3f803f80,0x3f803f80,0x3f803f80,
  0x3f803f80,0x3f803f80,0x3f803f80,0x3f803f80,0x3f803f80,0x3f803f80,0x3f803f80,0x3f803f80,0x3f803f80,0x3f803f80,0x3f803f80,0x3f803f80,
  0x3f803f80,0x3f803f80,0x3f803f80,0x3f803f80,0x3f803f80,0x3f803f80,0x3f803f80,0x3f803f80,0x3f803f80,0x3f803f80,0x3f803f80,0x3f803f80,
  0x3f803f80,0x3f803f80,0x3f803f80,0x3f803f80,0x3f803f80,0x3f803f80,0x3f803f80,0x3f803f80,0x3f803f80,0x3f803f80,0x3f803f80,0x3f803f80,
  0x3f803f80,0x3f803f80,0x3f803f80,0x3f803f80,0x3f803f80,0x3f803f80,0x3f803f80,0x3f803f80,0x3f803f80,0x3f803f80,0x3f803f80,0x3f803f80,
  0x3f803f80,0x3f803f80,0x3f803f80,0x3f803f80,0x3f803f80,0x3f803f80,0x3f803f80,0x3f803f80,0x3f803f80,0x3f803f80,0x3f803f80,0x3f803f80,
  0x3f803f80,0x3f803f80,0x3f803f80,0x3f803f80,0x3f803f80,0x3f803f80,0x3f803f80,0x3f803f80,0x3f803f80,0x3f803f80,0x3f803f80,0x3f803f80,
  0x3f803f80,0x3f803f80,0x3f803f80,0x3f803f80,0x3f803f80,0x3f803f80,0x3f803f80,0x3f803f80,0x3f803f80,0x3f803f80,0x3f803f80,0x3f803f80,
  0x3f803f80,0x3f803f80,0x3f803f80,0x3f803f80,
};

__device__ __align__(128) float    g_part[16][8][2176];
__device__ __align__(128) float    g_kv[16][2176];
__device__ __align__(128) uint4    g_o[16 * 16 * 1024];
__device__ __align__(128) unsigned g_ocnt[2 * 16 * 32];
__device__ unsigned g_epoch[128];
#define GSTAMP(role, i) do {} while (0)
#define STAMP(role, i) do {} while (0)
#define PDUMP(role) do {} while (0)
#define PROF_SMEM 0

constexpr int STAGE_BYTES = 57344;
constexpr int OFF_H = 4 * 16384, OFF_VP = 9 * 16384, OFF_SPARE = 10 * 16384;
constexpr int OFF_XT = 172032, XT_STRIDE = 4112;
constexpr int OFF_BAR = 204928, OFF_EPOCH = OFF_BAR + 640, OFF_EX = OFF_BAR + 656, OFF_D = OFF_BAR + 672, OFF_SCALE = OFF_BAR + 704;
constexpr int OFF_F2F = 205824, OFF_F2I = 207872, OFF_F4 = 209920, OFF_ONES = 214016, OFF_KVB = 214016;
constexpr int OFF_STG = 219136, STG_STRIDE = 4352, SMEM_TOTAL = 232192 + PROF_SMEM;
enum { B_FULL1 = 0, B_EMPTY1 = 3, B_Q = 6, B_ODONE1 = 7, B_O1RDY = 8, B_H = 9, B_XRAW = 10, B_XT = 11, B_KV = 12, B_Y = 13, B_PKFREE = 14, B_AFREE = 15,
       B_STG = 18, B_ODONE = 24, B_XFREE = 25, B_FULL2 = 33, B_CONS2 = 49, B_SFREE = 62, B_COUNT = 63 };
__host__ __device__ constexpr int bar_count(int i) {
  return i < B_EMPTY1 ? 1 : i < B_Q ? 4 : i == B_XT ? 4 : i == B_H ? 3 : i >= B_SFREE ? 1 : i == B_KV ? 2 : i == B_Y ? 9 : i == B_PKFREE ? 8
       : (i >= B_AFREE && i < B_STG) ? 16 : (i == B_ODONE || i == B_ODONE1) ? 8 : (i >= B_XFREE && i < B_FULL2) ? 4
       : (i >= B_CONS2 && i <= B_CONS2 + 10) ? 4 : i >= B_CONS2 ? 2 : (i >= B_FULL2 && i < B_FULL2 + 7) ? 2 : 1;
}
__host__ __device__ constexpr uint64_t bar_counts(int r) {
  uint64_t v = 0;
  for (int w = 0; w < 11; w++) v |= (uint64_t)(bar_count(1 + 11 * r + w) - 1) << (4 * w);
  return v;
}
constexpr uint64_t SLOT_A = 0x9645296452964594ull;
constexpr uint64_t SLOT_B = 0x7310873108731026ull;
constexpr int SPIN_LIMIT = 1 << 22;
#define PKV CU_TENSOR_MAP_L2_PROMOTION_L2_128B
#define BPRE B_KV
#define PFD 3
#define PD1 400
#define PD2 100
#define E1C 2
#define OSP 4
#define QPF 6
#define TSPLIT 1
#define OC0 2
#define OC1 2
#define BSPL 4
#define BPACE 400
#define NPOS 0
#define O1POS 1
#define HL1 4
#define OCH 3
#define O1D 3
#define QPOS 2
#define HOLD2 13
#define A0COL 0
#define HSTART 1500
#define PACE 800
#define OC 1

__device__ __forceinline__ uint32_t smem_u32(const void* p) { return (uint32_t)__cvta_generic_to_shared(p); }
__device__ __forceinline__ void wg_fence() { asm volatile("wgmma.fence.sync.aligned;" ::: "memory"); }
__device__ __forceinline__ void wg_commit() { asm volatile("wgmma.commit_group.sync.aligned;" ::: "memory"); }
template <int N> __device__ __forceinline__ void wg_wait() { asm volatile("wgmma.wait_group.sync.aligned %0;" ::"n"(N) : "memory"); }
template <int N> __device__ __forceinline__ void keep(float (&d)[N]) {
#pragma unroll
  for (int i = 0; i < N; i++) asm volatile("" : "+f"(d[i])::"memory");
}
__device__ __forceinline__ uint64_t mkdesc(uint32_t addr, uint32_t lbo, uint32_t sbo, uint32_t swz) {
  uint32_t lo = ((addr & 0x3FFFF) >> 4) | ((lbo >> 4) << 16), hi = (sbo >> 4) | (swz << 30);
  return ((uint64_t)hi << 32) | lo;
}
__device__ __forceinline__ void mbar_init(uint32_t bar, int cnt) { asm volatile("mbarrier.init.shared::cta.b64 [%0], %1;" ::"r"(bar), "r"(cnt)); }
__device__ __forceinline__ void mbar_expect(uint32_t bar, int bytes) { asm volatile("mbarrier.arrive.expect_tx.shared::cta.b64 _, [%0], %1;" ::"r"(bar), "r"(bytes) : "memory"); }
__device__ __forceinline__ void mbar_arrive(uint32_t bar) { asm volatile("mbarrier.arrive.shared::cta.b64 _, [%0];" ::"r"(bar) : "memory"); }
__device__ __forceinline__ void mbar_arrive_cl(uint32_t bar, uint32_t cta) {
  asm volatile("{\n.reg .b32 r;\nmapa.shared::cluster.u32 r, %0, %1;\nmbarrier.arrive.shared::cluster.b64 _, [r];\n}\n" ::"r"(bar), "r"(cta) : "memory");
}
__device__ __forceinline__ void mbar_wait(uint32_t bar, uint32_t parity) {
  asm volatile("{\n.reg .pred p;\n.reg .u32 n;\nmov.u32 n, 0;\n"
               "W_%=:\nmbarrier.try_wait.parity.shared::cta.b64 p, [%0], %1;\n@p bra D_%=;\n"
               "add.u32 n, n, 1;\nsetp.lt.u32 p, n, %2;\n@p bra W_%=;\ntrap;\nD_%=:\n}\n" ::"r"(bar), "r"(parity), "n"(SPIN_LIMIT) : "memory");
}
__device__ __forceinline__ void fence_async() { asm volatile("fence.proxy.async.shared::cta;" ::: "memory"); }
__device__ __forceinline__ void bar_sync(int id) { asm volatile("bar.sync %0, 128;" ::"r"(id) : "memory"); }
__device__ __forceinline__ void tma2d(uint32_t dst, const CUtensorMap* m, int c0, int c1, uint32_t bar) {
  asm volatile("cp.async.bulk.tensor.2d.shared::cluster.global.mbarrier::complete_tx::bytes [%0], [%1, {%3, %4}], [%2];"
               ::"r"(dst), "l"(m), "r"(bar), "r"(c0), "r"(c1) : "memory");
}
__device__ __forceinline__ void tma2d_mc(uint32_t dst, const CUtensorMap* m, int c0, int c1, uint32_t bar) {
  asm volatile("cp.async.bulk.tensor.2d.shared::cluster.global.mbarrier::complete_tx::bytes.multicast::cluster [%0], [%1, {%3, %4}], [%2], %5;"
               ::"r"(dst), "l"(m), "r"(bar), "r"(c0), "r"(c1), "h"((uint16_t)3) : "memory");
}
__device__ __forceinline__ void tma3d(uint32_t dst, const CUtensorMap* m, int c0, int c1, int c2, uint32_t bar) {
  asm volatile("cp.async.bulk.tensor.3d.shared::cluster.global.mbarrier::complete_tx::bytes [%0], [%1, {%3, %4, %5}], [%2];"
               ::"r"(dst), "l"(m), "r"(bar), "r"(c0), "r"(c1), "r"(c2) : "memory");
}
__device__ __forceinline__ void tma4d(uint32_t dst, const CUtensorMap* m, int c0, int c1, int c2, int c3, uint32_t bar) {
  asm volatile("cp.async.bulk.tensor.4d.shared::cluster.global.mbarrier::complete_tx::bytes [%0], [%1, {%3, %4, %5, %6}], [%2];"
               ::"r"(dst), "l"(m), "r"(bar), "r"(c0), "r"(c1), "r"(c2), "r"(c3) : "memory");
}
__device__ __forceinline__ void bulk_ld(uint32_t dst, const void* src, int bytes, uint32_t bar) {
  asm volatile("cp.async.bulk.shared::cluster.global.mbarrier::complete_tx::bytes [%0], [%1], %2, [%3];" ::"r"(dst), "l"(src), "r"(bytes), "r"(bar) : "memory");
}
__device__ __forceinline__ void bulk_ld_mc(uint32_t dst, const void* src, int bytes, uint32_t bar) {
  asm volatile("cp.async.bulk.shared::cluster.global.mbarrier::complete_tx::bytes.multicast::cluster [%0], [%1], %2, [%3], %4;"
               ::"r"(dst), "l"(src), "r"(bytes), "r"(bar), "h"((uint16_t)3) : "memory");
}
__device__ __forceinline__ void tma2d_st(const CUtensorMap* m, uint32_t src, int c0, int c1) {
  asm volatile("cp.async.bulk.tensor.2d.global.shared::cta.bulk_group [%0, {%2, %3}], [%1];" ::"l"(m), "r"(src), "r"(c0), "r"(c1) : "memory");
}
__device__ __forceinline__ void pf_l2(const void* p, int bytes) { asm volatile("cp.async.bulk.prefetch.L2.global [%0], %1;" ::"l"(p), "r"(bytes) : "memory"); }
__device__ __forceinline__ void pf_t2d(const CUtensorMap* m, int c0, int c1) {
  asm volatile("cp.async.bulk.prefetch.tensor.2d.L2.global [%0, {%1, %2}];" ::"l"(m), "r"(c0), "r"(c1) : "memory");
}
__device__ __forceinline__ void pf_t3d(const CUtensorMap* m, int c0, int c1, int c2) {
  asm volatile("cp.async.bulk.prefetch.tensor.3d.L2.global [%0, {%1, %2, %3}];" ::"l"(m), "r"(c0), "r"(c1), "r"(c2) : "memory");
}
__device__ __forceinline__ void ldsm4(uint32_t (&r)[4], uint32_t a) {
  asm volatile("ldmatrix.sync.aligned.m8n8.x4.shared.b16 {%0,%1,%2,%3}, [%4];" : "=r"(r[0]), "=r"(r[1]), "=r"(r[2]), "=r"(r[3]) : "r"(a) : "memory");
}
__device__ __forceinline__ void ldsm4t(uint32_t (&r)[4], uint32_t a) {
  asm volatile("ldmatrix.sync.aligned.m8n8.x4.trans.shared.b16 {%0,%1,%2,%3}, [%4];" : "=r"(r[0]), "=r"(r[1]), "=r"(r[2]), "=r"(r[3]) : "r"(a) : "memory");
}
__device__ __forceinline__ void stsm4(uint32_t a, uint32_t r0, uint32_t r1, uint32_t r2, uint32_t r3) {
  asm volatile("stmatrix.sync.aligned.m8n8.x4.shared.b16 [%0], {%1,%2,%3,%4};" ::"r"(a), "r"(r0), "r"(r1), "r"(r2), "r"(r3) : "memory");
}
__device__ __forceinline__ uint32_t pk2(float lo, float hi) { uint32_t r; asm("cvt.rn.bf16x2.f32 %0, %1, %2;" : "=r"(r) : "f"(hi), "f"(lo)); return r; }
__device__ __forceinline__ uint32_t hmul(uint32_t a, uint32_t b) { uint32_t r; asm("mul.rn.bf16x2 %0, %1, %2;" : "=r"(r) : "r"(a), "r"(b)); return r; }
__device__ __forceinline__ uint32_t hadd(uint32_t a, uint32_t b) { uint32_t r; asm("add.rn.bf16x2 %0, %1, %2;" : "=r"(r) : "r"(a), "r"(b)); return r; }
__device__ __forceinline__ uint32_t hmax(uint32_t a, uint32_t b) { uint32_t r; asm("max.bf16x2 %0, %1, %2;" : "=r"(r) : "r"(a), "r"(b)); return r; }
__device__ __forceinline__ uint32_t hmin(uint32_t a, uint32_t b) { uint32_t r; asm("min.bf16x2 %0, %1, %2;" : "=r"(r) : "r"(a), "r"(b)); return r; }
__device__ __forceinline__ uint32_t hmaxabs(uint32_t a, uint32_t b) { uint32_t r; asm("max.xorsign.abs.bf16x2 %0, %1, %2;" : "=r"(r) : "r"(a), "r"(b)); return r; }
__device__ __forceinline__ float ex2(float x) { float r; asm("ex2.approx.ftz.f32 %0, %1;" : "=f"(r) : "f"(x)); return r; }
__device__ __forceinline__ float rcp_fast(float x) { float r; asm("rcp.approx.ftz.f32 %0, %1;" : "=f"(r) : "f"(x)); return r; }
__device__ __forceinline__ uint32_t phi2(float lo, float hi) {
  uint32_t t;
  asm("cvt.rn.relu.bf16x2.f32 %0, %1, %2;" : "=r"(t) : "f"(hi), "f"(lo));
  const uint32_t e = pk2(ex2(lo * 1.4426950408889634f), ex2(hi * 1.4426950408889634f));
  return hadd(hadd(t, hmin(e, 0x3F803F80u)), 0x35863586u);
}
__device__ __forceinline__ bool opaque_true() { uint32_t v; asm volatile("mov.u32 %0, %%nctaid.y;" : "=r"(v)); return v != 0; }
__device__ __forceinline__ int normalise(uint32_t (&v)[32], float fd) {
  const float f0 = fd + __uint_as_float(v[0] << 16);
  uint32_t m[4] = {hmaxabs(__float_as_uint(f0) >> 16, v[0]), v[1], v[2], v[3]};
#pragma unroll
  for (int i = 4; i < 32; i++) m[i & 3] = hmaxabs(m[i & 3], v[i]);
  m[0] = hmaxabs(hmaxabs(m[0], m[1]), hmaxabs(m[2], m[3]));
  const int e = min(max((int)(__reduce_max_sync(~0u, max(m[0] & 0x7FFFu, (m[0] >> 16) & 0x7FFFu)) >> 7), 1), 253);
  if (e > 141) {
#pragma unroll
    for (int i = 0; i < 32; i++) v[i] = hmul(v[i], 0x07000700u);
  }
  const uint32_t sc = (e > 141 ? 255 - e : 142 - e) * 0x00800080u;
#pragma unroll
  for (int i = 0; i < 32; i++) {
    const uint32_t a = hmul(v[i], sc);
    v[i] = (a & 0x0FFF0FFFu) * 7 + a;
  }
  v[0] = __byte_perm(v[0], __half_as_ushort(__float2half_rn(f0 * __uint_as_float((254 - e) << 23))), 0x3254);
  return e;
}
__device__ __forceinline__ void poll_ge(const unsigned* p, unsigned target) {
#pragma unroll 1
  for (int n = 0; n < SPIN_LIMIT; n++) {
    unsigned v;
    asm volatile("ld.relaxed.gpu.global.u32 %0, [%1];" : "=r"(v) : "l"(p) : "memory");
    if (__all_sync(~0u, (int)(v - target) >= 0)) { asm volatile("fence.acquire.gpu;" ::: "memory"); return; }
  }
  __trap();
}

__device__ __forceinline__ bool elect_one() {
  uint32_t p;
  asm volatile("{\n.reg .pred p;\nelect.sync _|p, 0xffffffff;\nselp.u32 %0, 1, 0, p;\n}\n" : "=r"(p));
  return p;
}
__device__ __forceinline__ uint4 ld_nc4(const void* p) {
  uint4 v;
  asm volatile("ld.global.nc.L1::no_allocate.v4.u32 {%0,%1,%2,%3}, [%4];" : "=r"(v.x), "=r"(v.y), "=r"(v.z), "=r"(v.w) : "l"(p));
  return v;
}
__device__ __forceinline__ void st_cg4(void* p, uint4 v) {
  asm volatile("st.global.cg.v4.u32 [%0], {%1,%2,%3,%4};" ::"l"(p), "r"(v.x), "r"(v.y), "r"(v.z), "r"(v.w) : "memory");
}
__device__ __forceinline__ uint32_t mapa(uint32_t a, uint32_t cta) { uint32_t r; asm("mapa.shared::cluster.u32 %0, %1, %2;" : "=r"(r) : "r"(a), "r"(cta)); return r; }
__device__ __forceinline__ void st_async(uint32_t a, uint32_t v, uint32_t bar) {
  asm volatile("st.async.weak.shared::cluster.mbarrier::complete_tx::bytes.b32 [%0], %1, [%2];" ::"r"(a), "r"(v), "r"(bar) : "memory");
}
__device__ __forceinline__ void st_async4(uint32_t a, uint32_t x, uint32_t y, uint32_t z, uint32_t w, uint32_t bar) {
  asm volatile("st.async.weak.shared::cluster.mbarrier::complete_tx::bytes.v4.b32 [%0], {%1,%2,%3,%4}, [%5];" ::"r"(a), "r"(x), "r"(y), "r"(z), "r"(w), "r"(bar) : "memory");
}
__device__ __forceinline__ void tma3d_st(const CUtensorMap* m, uint32_t src, int c0, int c1, int c2) {
  asm volatile("cp.async.bulk.tensor.3d.global.shared::cta.bulk_group [%0, {%2, %3, %4}], [%1];" ::"l"(m), "r"(src), "r"(c0), "r"(c1), "r"(c2) : "memory");
}
__device__ __forceinline__ uint4 ld_rlx4(const void* p) {
  uint4 v;
  asm volatile("{\n.reg .b128 t;\n.reg .b64 a, b;\nld.relaxed.gpu.global.b128 t, [%4];\nmov.b128 {a, b}, t;\nmov.b64 {%0, %1}, a;\nmov.b64 {%2, %3}, b;\n}\n"
               : "=r"(v.x), "=r"(v.y), "=r"(v.z), "=r"(v.w) : "l"(p) : "memory");
  return v;
}
__device__ __forceinline__ void ld_stale4(uint4& v, const void* p, uint32_t tag) {
  asm volatile("{\n.reg .b128 t;\n.reg .b64 a, b;\n.reg .b32 x;\n.reg .pred p;\n"
               "lop3.b32 x, %0, %5, 1, 0x28;\nsetp.ne.u32 p, x, 0;\n"
               "mov.b64 a, {%0, %1};\nmov.b64 b, {%2, %3};\nmov.b128 t, {a, b};\n"
               "@p ld.relaxed.gpu.global.b128 t, [%4];\n"
               "mov.b128 {a, b}, t;\nmov.b64 {%0, %1}, a;\nmov.b64 {%2, %3}, b;\n}\n"
               : "+r"(v.x), "+r"(v.y), "+r"(v.z), "+r"(v.w) : "l"(p), "r"(tag) : "memory");
}
__device__ __forceinline__ void st_tag4(void* p, float a, float b, float c, float d, uint32_t tag) {
  asm volatile("{\n.reg .b128 t;\n.reg .b64 a, b;\nmov.b64 a, {%1, %2};\nmov.b64 b, {%3, %4};\nmov.b128 t, {a, b};\nst.relaxed.gpu.global.b128 [%0], t;\n}\n"
               ::"l"(p), "r"((__float_as_uint(a) & ~1u) | tag), "f"(b), "f"(c), "f"(d) : "memory");
}
__device__ __forceinline__ uint32_t stale8(const uint4 (&f)[8], uint32_t tag) {
  uint32_t r[4];
#pragma unroll
  for (int i = 0; i < 4; i++) asm("lop3.b32 %0, %1, %2, %3, 0x7E;" : "=r"(r[i]) : "r"(f[2 * i].x), "r"(f[2 * i + 1].x), "r"(tag));
  asm("lop3.b32 %0, %0, %1, %2, 0xFE;" : "+r"(r[0]) : "r"(r[1]), "r"(r[2]));
  return r[0] | r[3];
}

struct ConvC { uint32_t a1[2][4], wa[2], wb[2], sg; };
__device__ __forceinline__ uint64_t dsc(uint32_t lo, uint32_t hi) { return ((uint64_t)hi << 32) | lo; }
__device__ __forceinline__ uint32_t hfma(uint32_t a, uint32_t b, uint32_t c) { uint32_t r; asm("fma.rn.f16x2 %0, %1, %2, %3;" : "=r"(r) : "r"(a), "r"(b), "r"(c)); return r; }
__device__ __forceinline__ uint32_t hfnma(uint32_t a, uint32_t b, uint32_t c) { uint32_t r; asm("{.reg .b32 n; neg.f16x2 n, %1; fma.rn.f16x2 %0, n, %2, %3;}" : "=r"(r) : "r"(a), "r"(b), "r"(c)); return r; }
__device__ __forceinline__ uint32_t hmul16(uint32_t a, uint32_t b) { uint32_t r; asm("mul.rn.f16x2 %0, %1, %2;" : "=r"(r) : "r"(a), "r"(b)); return r; }
template <int N> __device__ __forceinline__ void keepu(uint32_t (&d)[N]) {
#pragma unroll
  for (int i = 0; i < N; i++) asm volatile("" : "+r"(d[i])::"memory");
}
__device__ __forceinline__ void conv_m1(const ConvC& K, uint32_t (&u)[16], uint32_t l) {
  wg_fence();
  wgmma_hrs_n64<1>(u, K.a1[0][0], K.a1[0][1], K.a1[0][2], K.a1[0][3], dsc(l, 32), 0);
  wgmma_hrs_n64<1>(u, K.a1[1][0], K.a1[1][1], K.a1[1][2], K.a1[1][3], dsc(l + 16, 32), 1);
  wg_commit();
}
__device__ __forceinline__ void conv_s2(const ConvC& K, uint32_t (&u)[16], uint32_t (&Z)[2][8], uint32_t dfl) {
  uint32_t fr[8], fi[8];
#pragma unroll
  for (int c = 0; c < 8; c++) {
    const uint32_t r = hfma(K.wa[c & 1], u[2 * c + 1], u[2 * c]);
    fi[c] = hfma(K.wb[c & 1], r, u[2 * c + 1]);
    fr[c] = hfma(K.wa[c & 1], fi[c], r);
  }
  wg_fence();
#pragma unroll
  for (int p = 0; p < 2; p++) {
    wgmma_hrs_n32<0>(Z[p], fr[4 * p], fr[4 * p + 2], fr[4 * p + 1], fr[4 * p + 3], dsc(dfl, 32), 0);
    wgmma_hrs_n32<0>(Z[p], fi[4 * p], fi[4 * p + 2], fi[4 * p + 1], fi[4 * p + 3], dsc(dfl + 16, 32), 1);
  }
  wg_commit();
}
__device__ __forceinline__ void conv_win(const ConvC& K, const uint32_t (&X)[2][8], uint32_t (&W)[2][8]) {
#pragma unroll
  for (int b = 0; b < 4; b++)
#pragma unroll
    for (int c = 0; c < 2; c++) {
      const uint32_t xr = X[b >> 1][2 * c + (b & 1)], xi = X[b >> 1][4 + 2 * c + (b & 1)];
      const int a = b ? b - 1 : 0;
      W[b >> 1][2 * c + (b & 1)] = b ? hfnma(K.sg, X[a >> 1][4 + 2 * c + (a & 1)], xr) : hmul16(xr, 0x3C003C00u);
      W[b >> 1][4 + 2 * c + (b & 1)] = b ? hfma(K.sg, X[a >> 1][2 * c + (a & 1)], xi) : hmul16(xi, 0x3C003C00u);
    }
}
template <int p>
__device__ __forceinline__ void conv_pw(uint32_t (&X)[2][8], uint32_t (&H)[2][8], uint32_t (&V)[8], uint32_t dil) {
  uint32_t pr[2][2], pi[2][2];
#pragma unroll
  for (int jj = 0; jj < 2; jj++)
#pragma unroll
    for (int c = 0; c < 2; c++) {
      const int j = 2 * p + jj;
      uint32_t sr = 0, si = 0;
#pragma unroll
      for (int a = 0; a <= j; a++) {
        const int b = j - a;
        const uint32_t hr = H[a >> 1][2 * c + (a & 1)], hi = H[a >> 1][4 + 2 * c + (a & 1)];
        const uint32_t xr = X[b >> 1][2 * c + (b & 1)], xi = X[b >> 1][4 + 2 * c + (b & 1)];
        sr = a == 0 ? hmul16(hr, xr) : hfma(hr, xr, sr);
        si = a == 0 ? hmul16(hr, xi) : hfma(hr, xi, si);
        sr = hfnma(hi, xi, sr);
        si = hfma(hi, xr, si);
      }
      pr[jj][c] = sr; pi[jj][c] = si;
    }
  wg_fence();
  wgmma_hrs_n32<0>(V, pr[0][0], pr[1][0], pr[0][1], pr[1][1], dsc(dil, 32), 0);
  wgmma_hrs_n32<0>(V, pi[0][0], pi[1][0], pi[0][1], pi[1][1], dsc(dil + 16, 32), 1);
  wg_commit();
}
template <int p>
__device__ __forceinline__ void conv_it(const ConvC& K, uint32_t (&V)[8], uint32_t vst) {
#pragma unroll
  for (int jj = 0; jj < 2; jj++) {
    uint32_t wr[2], wi[2];
#pragma unroll
    for (int c = 0; c < 2; c++) {
      const uint32_t r = hfnma(K.wa[c], V[4 + 2 * c + jj], V[2 * c + jj]);
      wi[c] = hfnma(K.wb[c], r, V[4 + 2 * c + jj]);
      wr[c] = hfnma(K.wa[c], wi[c], r);
    }
    stsm4(vst + (2 * p + jj) * 2048, wr[0], wr[1], wi[0], wi[1]);
  }
}
__device__ __forceinline__ void conv_m4(uint32_t (&y)[8], uint32_t (&a)[4][4], uint32_t d4l) {
  wg_fence();
  wgmma_hrs_n32<0>(y, a[0][0], a[0][1], a[0][2], a[0][3], dsc(d4l, 64), 0);
#pragma unroll
  for (int s = 1; s < 4; s++) wgmma_hrs_n32<0>(y, a[s][0], a[s][1], a[s][2], a[s][3], dsc(d4l + s * 16, 64), 1);
  wg_commit();
}

struct Params {
  CUtensorMap tmX, tmW, tmWo, tmWo1, tmK, tmV, tmQ, tmOA, tmOB;
  const __nv_bfloat16 *shift_k, *h, *D, *x, *w, *wo, *q;
  float *part, *kv;
  uint4* o;
  unsigned *ocnt, *epoch;
  const uint32_t *thr, *img;
};

__global__ void __cluster_dims__(2, 1, 1) __launch_bounds__(384, 1) fused_kernel(const __grid_constant__ Params P) {
  extern __shared__ __align__(1024) uint8_t smem[];
  const uint32_t sb = smem_u32(smem);
  const uint32_t bars = sb + OFF_BAR;
  const int tid = threadIdx.x, lane = tid & 31;
  const int warp = __shfl_sync(~0u, tid >> 5, 0);
  const int rank = blockIdx.x & 1, cl = blockIdx.x >> 1;
  const int mb = cl < 4 ? 4 + cl : cl < 36 ? (cl - 4) >> 3 : 4 + (cl - 36) / 7;
  const int hb = (cl - 36) % 7;
  const int hq = cl < 4 ? A0COL : cl < 36 ? (cl - 4) & 7 : hb + (hb >= A0COL);
  const int hp = 2 * hq + rank;
  const int rb = 2 * mb + (hq >> 2), cb = hq & 3;
#define BAR(i) (bars + 8 * (i))

  if (tid == 0) { STAMP(0, 0); GSTAMP(0, 30); }
  if (warp == 8) {
    if (elect_one()) {
      mbar_init(BAR(B_FULL1), 1);
      asm volatile("fence.mbarrier_init.release.cluster;" ::: "memory");
      mbar_expect(BAR(B_FULL1), STAGE_BYTES);
      tma3d(sb + 32768, &P.tmW, hp * 64, 0, 0, BAR(B_FULL1));
    }
    if (lane == 0) STAMP(3, 21);
  } else if (lane == 0) {
    const int wi = warp - (warp > 8);
#pragma unroll
    for (int r = 0; r < 6; r++)
      if (r < 5 || wi < B_COUNT - 56) mbar_init(BAR(1 + 11 * r + wi), ((uint32_t)(bar_counts(r) >> (4 * wi)) & 15) + 1);
    asm volatile("fence.mbarrier_init.release.cluster;" ::: "memory");
  }
  if (tid == 0) STAMP(2, 6);
  asm volatile("barrier.cluster.arrive.relaxed.aligned;\nbarrier.cluster.wait.aligned;" ::: "memory");
  if (warp == 8 && elect_one()) tma2d_mc(sb + rank * 16384, &P.tmX, 0, mb * 256 + rank * 128, BAR(B_FULL1));
  if (tid == 256) STAMP(2, 7);

  if (warp < 8) {
    asm volatile("setmaxnreg.inc.sync.aligned.u32 224;");
    const int wg = warp >> 2, w = warp & 3, g = lane >> 2, q = lane & 3, t = tid & 127;
    const bool elect = (t == 0);
    const uint32_t s16 = (sb & 0x3FFFF) >> 4;
    constexpr uint32_t SW128 = 64 | (1u << 30);
    uint32_t pq[2][16];
    ConvC K;
    {
      float acc[2][96];
      int st = 0, ph = 0;
#pragma unroll 1
      for (int kb = 0; kb < 14; kb++) {
        mbar_wait(BAR(B_FULL1 + st), ph);
        if (kb == 0 && elect) { STAMP(wg, 1); GSTAMP(wg, 26); }
        if (kb == 8 && elect) { STAMP(wg, 16); GSTAMP(wg, 25); }
        if (tid == 0) STAMP(2, 8 + kb);
        const uint32_t da = s16 + st * (STAGE_BYTES >> 4) + wg * 1024 + (1 << 16);
        const uint32_t db = s16 + st * (STAGE_BYTES >> 4) + 2048 + (512 << 16);
        wg_fence();
#pragma unroll
        for (int ks = 0; ks < 4; ks++) {
          wgmma_ss_n192<0, 1>(acc[0], dsc(da + ks * 2, SW128), dsc(db + ks * 128, SW128), (kb | ks) != 0);
          wgmma_ss_n192<0, 1>(acc[1], dsc(da + 512 + ks * 2, SW128), dsc(db + ks * 128, SW128), (kb | ks) != 0);
        }
        wg_commit();
        wg_wait<1>();
        if (kb > 0 && t < 2) mbar_arrive_cl(BAR(B_EMPTY1 + (st == 0 ? 2 : st - 1)), t);
        if (++st == 3) { st = 0; ph ^= 1; }
      }
#define TAIL_MMA(mt, stage) do { wg_fence(); _Pragma("unroll") for (int ks = 0; ks < 4; ks++) \
        wgmma_ss_n192<0, 1>(acc[mt], dsc(s16 + (stage) * (STAGE_BYTES >> 4) + wg * 1024 + (mt) * 512 + (1 << 16) + ks * 2, SW128), \
                            dsc(s16 + (stage) * (STAGE_BYTES >> 4) + 2048 + (512 << 16) + ks * 128, SW128), 1); wg_commit(); } while (0)
      mbar_wait(BAR(B_FULL1 + 2), 0);
      TAIL_MMA(0, 2);
      wg_wait<1>();
      if (t < 2) mbar_arrive_cl(BAR(B_EMPTY1 + 1), t);
      mbar_wait(BAR(B_FULL1 + 0), 1);
      TAIL_MMA(0, 0);
      TAIL_MMA(1, 2);
      if (!TSPLIT) TAIL_MMA(1, 0);
      const uint32_t lrow = sb + wg * 16384 + (16 * w + 8 * ((lane >> 3) & 1) + (lane & 7)) * 128 + (((lane >> 4) ^ (lane & 7)) << 4);
#define E1K(mt, i) do { if (opaque_true()) { _Pragma("unroll") for (int j = (i); j < (i) + 2; j++) { \
          const float* a = &acc[mt][32 + 8 * j]; const float* b = a + 32; const uint32_t o = (lrow ^ (j * 32)) + (mt) * 8192; \
          stsm4(o + 2 * STAGE_BYTES, pk2(b[0], b[1]), pk2(b[2], b[3]), pk2(b[4], b[5]), pk2(b[6], b[7])); \
          stsm4(o, phi2(a[0], a[1]), phi2(a[2], a[3]), phi2(a[4], a[5]), phi2(a[6], a[7])); } } } while (0)
#define E1Q(mt) do { if (opaque_true()) { _Pragma("unroll") for (int i = 0; i < 16; i++) pq[mt][i] = phi2(acc[mt][2 * i], acc[mt][2 * i + 1]); } } while (0)
      mbar_wait(BAR(B_EMPTY1 + 1), 0);
      if (TSPLIT) wg_wait<1>(); else wg_wait<2>();
      keep(acc[0]);
      if (elect) STAMP(wg, 18);
      E1K(0, 0);
      if (TSPLIT) TAIL_MMA(1, 0);
      E1K(0, 2);
      if (elect) STAMP(wg, 19);
      if (QPOS == 0) E1Q(0);
      if (elect) STAMP(wg, 20);
      {
        const uint4* ct = (const uint4*)P.thr + t;
#pragma unroll
        for (int s = 0; s < 2; s++) { const uint4 u = ld_nc4(ct + s * 128); K.a1[s][0] = u.x; K.a1[s][1] = u.y; K.a1[s][2] = u.z; K.a1[s][3] = u.w; }
        const uint4 u = ld_nc4(ct + 2 * 128);
        K.wa[0] = u.x; K.wa[1] = u.y; K.wb[0] = u.z; K.wb[1] = u.w;
        K.sg = (lane & 4) ? 0xBC00BC00u : 0x3C003C00u;
      }
      mbar_wait(BAR(B_XT), 0);
      const uint32_t tag = ~*(volatile unsigned*)(smem + OFF_EPOCH) & 1;
      wg_wait<0>();
      keep(acc[1]);
      if (t < 2) mbar_arrive_cl(BAR(B_EMPTY1 + 0), t);
      if (elect) { STAMP(wg, 2); GSTAMP(wg, 27); }
      E1K(1, 0);
      E1K(1, 2);
      fence_async();
      bar_sync(1 + wg);
      if (elect) STAMP(wg, 3);
      float kva[36];
      wg_fence();
#pragma unroll
      for (int ks = 0; ks < 8; ks++) {
        const uint32_t vb = (2 * STAGE_BYTES >> 4) + wg * 1024 + ks * 128;
        wgmma_ss_n72<1, 1>(kva, dsc(s16 + wg * 1024 + ks * 128 + (1 << 16), SW128), dsc(s16 + vb + (((OFF_ONES >> 4) - vb) << 16), SW128), ks != 0);
      }
      wg_commit();
      if (QPOS == 1) E1Q(0);
      wg_wait<0>();
      keep(kva);
      if (elect) STAMP(wg, 24);
      {
        float4 p[5];
#pragma unroll
        for (int c = 0; c < 4; c++)
          p[c] = w < 2 ? make_float4(kva[4 * c], kva[4 * c + 1], kva[4 * c + 2], kva[4 * c + 3])
                       : make_float4(kva[16 + 4 * c], kva[17 + 4 * c], kva[18 + 4 * c], kva[19 + 4 * c]);
        p[4] = make_float4(kva[32], kva[34], __shfl_down_sync(~0u, kva[32], 4), __shfl_down_sync(~0u, kva[34], 4));
        float4* hand = (float4*)(smem + STAGE_BYTES) + t;
        float4* handz = (float4*)(smem + OFF_ONES + 2048) + t;
        if ((w >> 1) != wg) {
#pragma unroll
          for (int c = 0; c < 4; c++) hand[c * 128] = p[c];
          *handz = p[4];
          asm volatile("bar.arrive %0, 128;" ::"r"(5 + (w >> 1)) : "memory");
        } else {
          float* dst = P.part + (hp * 8 + mb) * 2176;
          asm volatile("bar.sync %0, 128;" ::"r"(5 + (w >> 1)) : "memory");
#pragma unroll
          for (int c = 0; c < 5; c++) { const float4 u = c < 4 ? hand[c * 128] : *handz; p[c].x += u.x; p[c].y += u.y; p[c].z += u.z; p[c].w += u.w; }
#pragma unroll
          for (int c = 0; c < 5; c++)
            if (c < 4 || !(lane & 7)) st_tag4(c < 4 ? dst + (c * 128 + t) * 4 : dst + 2048 + 16 * w + 2 * g, p[c].x, p[c].y, p[c].z, p[c].w, tag);
        }
        __syncwarp();
        if (lane == 0) mbar_arrive(BAR(B_PKFREE));
      }
      if (elect) STAMP(wg, 4);
      if (QPOS == 2) E1Q(0);
      E1Q(1);
    }
    if (elect) STAMP(wg, 17);
    mbar_wait(BAR(B_H), 0);
    mbar_wait(BAR(B_PKFREE), 0);
    if (elect) STAMP(wg, 5);
    {
      const uint32_t dfl = s16 + (OFF_F2F >> 4) + (8 << 16), dil = s16 + (OFF_F2I >> 4) + (8 << 16), d4l = s16 + (OFF_F4 >> 4) + (8 << 16);
      const uint32_t xl = s16 + (OFF_XT >> 4) + 4 * wg * (XT_STRIDE >> 4) + (8 << 16);
      const uint32_t hl = s16 + (OFF_H >> 4) + wg * 512 + (8 << 16);
      uint32_t vst = sb + wg * 8192 + w * 512 + lane * 16, vld = sb + wg * 8192 + w * 2048 + lane * 16;
      uint32_t ya = mapa(sb + OFF_XT + 4 * wg * XT_STRIDE + (2 * rank + (w & 1)) * 1024 + lane * 16, w >> 1);
      const uint32_t ybar = mapa(BAR(B_Y), w >> 1);
      asm volatile("" : "+r"(vst), "+r"(vld), "+r"(ya));
      uint32_t ux[16], uh[16], W[2][8], V0[8], V1[8], y[8], a[4][4];
      uint4* const ot = P.o + ((2 * mb + wg) * 16 + hq) * 1024 + (16 * w + g) * 8 + ((4 * rank + q) ^ g);
#define YOUT(i) do { if ((w >> 1) == rank) { \
          asm volatile("st.shared.v4.b32 [%0], {%1,%2,%3,%4};" ::"r"(ya + (i) * XT_STRIDE), "r"(y[0]), "r"(y[2]), "r"(y[4]), "r"(y[6]) : "memory"); \
          asm volatile("st.shared.v4.b32 [%0], {%1,%2,%3,%4};" ::"r"(ya + (i) * XT_STRIDE + 512), "r"(y[1]), "r"(y[3]), "r"(y[5]), "r"(y[7]) : "memory"); \
        } else { \
          mbar_wait(BAR(B_XFREE + 4 * wg + (i)), 0); \
          st_async4(ya + (i) * XT_STRIDE, y[0], y[2], y[4], y[6], ybar); \
          st_async4(ya + (i) * XT_STRIDE + 512, y[1], y[3], y[5], y[7], ybar); } } while (0)
      auto ocalc = [&](const int hh) {
        if (hh == 0) {
          if (elect) STAMP(wg, 8);
          mbar_wait(BAR(B_KV), 0);
          if (elect) STAMP(wg, 9);
        }
        float oa[2][20];
        wg_fence();
#pragma unroll
        for (int m = 0; m < 4; m++) {
          const uint32_t* p = &pq[m & 1][8 * hh + 4 * (m >> 1)];
          wgmma_rs_n40<1>(oa[m & 1], p[0], p[1], p[2], p[3], dsc(s16 + (OFF_KVB >> 4) + hh * 160 + (m >> 1) * 16 + (8 << 16), 32), m >> 1);
        }
        wg_commit();
        wg_wait<0>();
#pragma unroll
        for (int mt = 0; mt < 2; mt++) {
          float (&o)[20] = oa[mt];
          keep(o);
          const uint32_t den = hadd(pk2(o[16], o[18]), 0x35863586u);
#pragma unroll
          for (int r = 0; r < 2; r++) {
            const float ri = rcp_fast(__uint_as_float(r ? (den & 0xFFFF0000u) : (den << 16)));
            uint4 u;
            u.x = pk2(o[2 * r] * ri, o[2 * r + 1] * ri);
            u.y = pk2(o[4 + 2 * r] * ri, o[5 + 2 * r] * ri);
            u.z = pk2(o[8 + 2 * r] * ri, o[9 + 2 * r] * ri);
            u.w = pk2(o[12 + 2 * r] * ri, o[13 + 2 * r] * ri);
            st_cg4(ot + hh * 8 * 1024 + (64 * mt + 8 * r) * 8, u);
          }
        }
        __syncwarp();
        if (lane == 0) mbar_arrive(BAR(hh ? B_ODONE1 : B_ODONE));
        if (hh == 0 && elect) STAMP(wg, 10);
      };
      uint32_t X[4][2][8], H[4][2][8];
      conv_m1(K, ux, xl);
      conv_m1(K, uh, hl);
      wg_wait<1>(); keepu(ux);
      if (lane == 0) mbar_arrive_cl(BAR(B_XFREE + 4 * wg), rank ^ 1);
      conv_s2(K, ux, X[0], dfl);
      wg_wait<1>(); keepu(uh);
      conv_s2(K, uh, H[0], dfl);
#pragma unroll
      for (int i = 0; i < 4; i++) {
        const bool nx = i < 3;
        const int n = nx ? i + 1 : i;
        const uint32_t vo = (i & 1) ? OFF_H + (i >> 1) * 16384 : OFF_VP;
        if (2 * i == OCH) ocalc(0);
        if (2 * i == OCH + O1D) ocalc(1);
        if (nx) {
          conv_m1(K, ux, xl + n * (XT_STRIDE >> 4));
          conv_m1(K, uh, hl + (n >> 1) * 1024 + (n & 1) * 256);
        }
        if (2 * i != OCH && 2 * i != OCH + O1D) { if (nx) { if (i > 0) wg_wait<3>(); else wg_wait<2>(); } else wg_wait<1>(); }
        keepu(X[i][0]); keepu(X[i][1]); keepu(H[i][0]); keepu(H[i][1]);
        conv_win(K, X[i], W);
        conv_pw<0>(W, H[i], V0, dil);
        conv_pw<1>(W, H[i], V1, dil);
        wg_wait<2>();
        if (i > 0) { keepu(y); YOUT(i - 1); }
        if (2 * i + 1 == OCH) ocalc(0);
        if (2 * i + 1 == OCH + O1D) ocalc(1);
        if (nx) {
          keepu(ux); keepu(uh);
          if (lane == 0) mbar_arrive_cl(BAR(B_XFREE + 4 * wg + n), rank ^ 1);
          conv_s2(K, ux, X[n], dfl);
          wg_wait<1>();
        } else wg_wait<0>();
        keepu(V0); keepu(V1);
        conv_it<0>(K, V0, vst + vo);
        conv_it<1>(K, V1, vst + vo);
        bar_sync(1 + wg);
#pragma unroll
        for (int s = 0; s < 4; s++) ldsm4t(a[s], vld + vo + s * 512);
        if (nx) conv_s2(K, uh, H[n], dfl);
        conv_m4(y, a, d4l);
        if (i > 0 && lane < 2) mbar_arrive_cl(BAR(B_AFREE + i - 1), lane);
        if (elect && i < 3) STAMP(wg, i < 2 ? 6 + i : 9 + i);
      }
      wg_wait<0>(); keepu(y);
      YOUT(3);
      __syncwarp();
      if (lane == 0) mbar_arrive(BAR(B_Y));
      if (elect) STAMP(wg, 12);
    }
    {
      float acc[64];
#pragma unroll 1
      for (int kb = 0; kb < 16; kb++) {
        mbar_wait(BAR(B_FULL2 + kb), 0);
        if (kb == 0 && elect) { STAMP(wg, 13); GSTAMP(wg, 28); }
        const uint32_t da = s16 + ((uint32_t)(SLOT_A >> (4 * kb)) & 15) * 1024 + wg * 512 + (1 << 16);
        const uint32_t db = s16 + ((uint32_t)(SLOT_B >> (4 * kb)) & 15) * 1024 + (512 << 16);
        if (kb == HOLD2 && wg == 0) asm volatile("bar.sync 3, 256;" ::: "memory");
        wg_fence();
#pragma unroll
        for (int ks = 0; ks < 4; ks++) wgmma_ss_n128<0, 1>(acc, dsc(da + ks * 2, SW128), dsc(db + ks * 128, SW128), (kb | ks) != 0);
        wg_commit();
        if (HOLD2 < 16 && kb == 15 && wg == 1) asm volatile("bar.arrive 3, 256;" ::: "memory");
        wg_wait<1>();
        if (kb > 0 && kb < 13 && t < 2 && (kb <= 11 || t == rank)) mbar_arrive_cl(BAR(B_CONS2 + kb - 1), t);
      }
      wg_wait<0>();
      keep(acc);
      if (elect) { STAMP(wg, 14); GSTAMP(wg, 29); }
      mbar_wait(BAR(B_CONS2 + 11), 0);
      const uint32_t stg = sb + ((uint32_t)((wg ? SLOT_A : SLOT_B) >> 44) & 15) * 16384;
      const uint32_t lrow = stg + (16 * w + 8 * ((lane >> 3) & 1) + (lane & 7)) * 128 + (((lane >> 4) ^ (lane & 7)) << 4);
#pragma unroll
      for (int cp = 0; cp < 8; cp++) {
        const float* a = &acc[8 * cp];
        stsm4((lrow ^ ((cp & 3) * 32)) + (cp >> 2) * 8192, pk2(a[0], a[1]), pk2(a[2], a[3]), pk2(a[4], a[5]), pk2(a[6], a[7]));
      }
      fence_async();
      bar_sync(1 + wg);
      if (elect) {
        const int col = 1024 + 256 * cb + 128 * rank, row = 128 * rb + 64 * wg;
        tma2d_st(&P.tmOB, stg, col, row);
        tma2d_st(&P.tmOB, stg + 8192, col + 64, row);
        asm volatile("cp.async.bulk.commit_group;\ncp.async.bulk.wait_group.read 0;" ::: "memory");
        STAMP(wg, 15); GSTAMP(wg, 31); PDUMP(wg);
      }
    }
  } else {
    asm volatile("setmaxnreg.dec.sync.aligned.u32 56;");
    if (warp == 8) {
      if (lane == 0) STAMP(3, 20);
      int st = 1, ph = 1;
      const uint8_t* pfx = (const uint8_t*)P.x + (mb * 256 + hp * 16 + (lane & 15)) * 2048;
      const uint8_t* pfw = (const uint8_t*)P.w + (mb * 8 + (lane & 7)) * 6144 + (lane >> 3) * 2048 + hp * 128;
#pragma unroll 1
      for (int kb = 1; kb < 16; kb++) {
        if (kb >= 3) mbar_wait(BAR(B_EMPTY1 + st), ph);
        const uint32_t sa = sb + st * STAGE_BYTES;
        if (elect_one()) {
          mbar_expect(BAR(B_FULL1 + st), STAGE_BYTES);
          tma2d_mc(sa + rank * 16384, &P.tmX, kb * 64, mb * 256 + rank * 128, BAR(B_FULL1 + st));
          tma3d(sa + 32768, &P.tmW, hp * 64, kb * 64, 0, BAR(B_FULL1 + st));
        }
        if (kb == 1 && lane == 0) STAMP(2, 24);
        if (PFD && kb >= 2) {
#pragma unroll 1
          for (int j = kb == 2 ? 3 : kb + PFD; j <= kb + PFD && j < 16; j++) {
            if (lane < 16) asm volatile("prefetch.global.L2 [%0];" ::"l"(pfx + j * 128));
            if (lane < 24) asm volatile("prefetch.global.L2 [%0];" ::"l"(pfw + j * (64 * 6144)));
          }
          if (kb >= QPF && kb < QPF + 8) asm volatile("prefetch.global.L2 [%0];" ::"l"((const uint8_t*)P.q + (blockIdx.x * 256 + (kb - QPF) * 32 + lane) * 128));
          if (kb >= 4)
            asm volatile("prefetch.global.L2 [%0];" ::"l"(kb < 12 ? (const uint8_t*)P.h + (blockIdx.x * 256 + (kb - 4) * 32 + lane) * 128
                                                                  : (const uint8_t*)P.wo + (blockIdx.x * 128 + (kb - 12) * 32 + lane) * 128));
        }
        if (++st == 3) { st = 0; ph ^= 1; }
      }
      if (lane == 0) STAMP(2, 1);
      const unsigned epoch = P.epoch[blockIdx.x];
#define SLOT(tab, kb) (sb + ((uint32_t)((tab) >> (4 * (kb))) & 15) * 16384)
#define LOAD_B(kb) tma4d(SLOT(SLOT_B, kb), &P.tmWo, 0, ((kb) >> 3) * 32, 2 * ((kb) & 7), 4 * cb + 2 * rank, BAR(B_FULL2 + (kb)))
#define LOAD_A(kb) bulk_ld_mc(SLOT(SLOT_A, kb) + rank * 8192, P.o + (rb * 16 + (kb)) * 1024 + rank * 512, 8192, BAR(B_FULL2 + (kb)))
      mbar_wait(BAR(B_EMPTY1 + 1), 0);
      if (lane == 0) mbar_arrive(BAR(B_SFREE));
      mbar_wait(BAR(B_EMPTY1 + 0), 1);
      {
        const uint32_t c0 = clock();
#pragma unroll 1
        for (int i = 0; i < 14; i++) {
          const int kb = i >> 1;
          if (i == 4) mbar_wait(BAR(B_PKFREE), 0);
          while (__any_sync(~0u, (uint32_t)clock() - c0 < i * BPACE)) __nanosleep(32);
          if (elect_one()) {
            if (!(i & 1)) mbar_expect(BAR(B_FULL2 + kb), 16384);
            tma4d(SLOT(SLOT_B, kb) + (i & 1) * 8192, &P.tmWo1, 0, 0, 2 * kb, 4 * cb + 2 * rank + (i & 1), BAR(B_FULL2 + kb));
            if (i == 0) mbar_expect(BAR(B_Q), 8192);
            if (i < 4) tma3d(sb + OFF_SPARE + 2048 * i, &P.tmQ, 16 * cl, 64 * rank + 32 * (i >> 1), 2 * ((i + 6) & 7), BAR(B_Q));
          }
        }
      }
      if (lane == 0) STAMP(2, 2);
      mbar_wait(BAR(B_AFREE), 0);
      if (elect_one()) mbar_expect(BAR(B_FULL2), 16384);
      {
        const uint32_t dst = SLOT(SLOT_A, 0) + rank * 8192;
        const uint4* src = P.o + rb * 16 * 1024 + rank * 512;
        poll_ge(&P.ocnt[rb * 32], 16 * (epoch + 1));
        asm volatile("fence.proxy.async.global;" ::: "memory");
        if (lane == 0) STAMP(2, 3);
        if (elect_one()) bulk_ld_mc(dst, src, 8192, BAR(B_FULL2));
        if (lane == 0) STAMP(3, 23);
      }
#pragma unroll 1
      for (int kb = 1; kb < 7; kb++) {
        mbar_wait(BAR(kb < 3 ? B_AFREE + kb : B_CONS2 + ((kb - 3) >> 1)), 0);
        if (elect_one()) { mbar_expect(BAR(B_FULL2 + kb), 16384); LOAD_A(kb); }
      }
#pragma unroll 1
      for (int kb = 7; kb < 16; kb++) {
        mbar_wait(BAR(B_CONS2 + kb - 5), 0);
        if (kb == 8) mbar_wait(BAR(B_O1RDY), 0);
        if (elect_one()) { mbar_expect(BAR(B_FULL2 + kb), 32768); LOAD_A(kb); LOAD_B(kb); }
      }
      if (lane == 0) { P.epoch[blockIdx.x] = epoch + 1; STAMP(2, 5); PDUMP(2); }
    } else {
      const uint32_t clk0 = __shfl_sync(~0u, (uint32_t)clock(), 0);
      const int hw = warp - 9, g = lane >> 2, q = lane & 3;
      const unsigned epoch = __shfl_sync(~0u, P.epoch[blockIdx.x], 0);
      const uint32_t tag = ~epoch & 1;
      const uint32_t stg = sb + OFF_STG + hw * STG_STRIDE, sbar = BAR(B_STG + 2 * hw);
      int ph = 0;
      {
        uint32_t tap[2][4];
#pragma unroll
        for (int cg = 0; cg < 2; cg++) {
          const uint2 u = __ldg((const uint2*)(P.shift_k + (16 * cl + 8 * cg + g) * 4));
          tap[cg][0] = __byte_perm(u.x, 0, 0x1010); tap[cg][1] = __byte_perm(u.x, 0, 0x3232);
          tap[cg][2] = __byte_perm(u.y, 0, 0x1010); tap[cg][3] = __byte_perm(u.y, 0, 0x3232);
        }
        if (hw == 0 && lane < 8) *(float*)(smem + OFF_D + 4 * lane) = __bfloat162float(P.D[blockIdx.x * 8 + lane]);
        if (hw == 1) asm volatile("prefetch.global.L2 [%0];" ::"l"(P.thr + (lane + 32 * (blockIdx.x & 1)) * 32));
        if (hw == 0 && elect_one()) {
          *(volatile unsigned*)(smem + OFF_EPOCH) = epoch;
          mbar_expect(BAR(B_XRAW), 16384);
          mbar_expect(BAR(B_Y), 16384 + 64);
        }
        for (int i = hw * 32 + lane; i < 528; i += 96) st_tag4(P.part + (hp * 8 + mb) * 2176 + 4 * i, 0.f, 0.f, 0.f, 0.f, tag ^ 1);
        if (hw < 2 || lane < 2) st_tag4(P.kv + hp * 2176 + (4 * (hw < 2 ? 64 * mb + 32 * hw + lane : 512 + 2 * mb + lane)), 0.f, 0.f, 0.f, 0.f, tag ^ 1);
        if (lane == 0) STAMP(3, hw);
        const uint32_t xo = sb + OFF_XT + g * XT_STRIDE + rank * 2048 + q * 4;
        const int krow = 8 + (lane & 7) - (lane >> 3);
        const uint32_t ka = stg + krow * 32 + ((krow & 4) << 2), va = stg + 2304 + lane * 32 + ((lane & 4) << 2);
        int b = 0;
#pragma unroll 1
        for (int ci = hw - 3; ci < 16; ci += 3) {
          const uint32_t bo = b ? OFF_F2F - OFF_STG : 0, bn = b ? 0 : OFF_F2F - OFF_STG;
          if (ci + 3 < 16) {
            while (__any_sync(~0u, (uint32_t)clock() - clk0 < HSTART + (ci + 3) * PACE)) __nanosleep(64);
            if (elect_one()) {
              mbar_expect(sbar + 8 * (b ^ 1), 2304 + 2048);
              tma2d(stg + bn, &P.tmK, 16 * cl, 1024 * rank + 64 * (ci + 3) - 8, sbar + 8 * (b ^ 1));
              tma2d(stg + bn + 2304, &P.tmV, 16 * cl, 1024 * rank + 64 * (ci + 3), sbar + 8 * (b ^ 1));
            }
          }
          if (ci >= 0) {
            mbar_wait(sbar + 8 * b, (ph >> b) & 1);
            ph ^= 1 << b;
#pragma unroll 1
            for (int grp = 0; grp < 2; grp++) {
#pragma unroll
              for (int cg = 0; cg < 2; cg++) {
                const uint32_t dst = mapa(xo + (ci >> 3) * 1024 + ((ci & 7) * 4 + 2 * grp) * 16, cg), xbar = mapa(BAR(B_XRAW), cg);
                uint32_t vv[4], kk[4][4];
                ldsm4t(vv, (va ^ (cg * 16)) + bo + grp * 1024);
#pragma unroll
                for (int rg = 0; rg < 4; rg++) ldsm4t(kk[rg], (ka ^ (cg * 16)) + bo + grp * 1024 + rg * 256);
#pragma unroll
                for (int rg = 0; rg < 4; rg++)
                  vv[rg] = hmul(hadd(hadd(hadd(hmul(kk[rg][3], tap[cg][3]), hmul(kk[rg][2], tap[cg][2])), hmul(kk[rg][1], tap[cg][1])), hmul(kk[rg][0], tap[cg][0])), vv[rg]);
                if (cg == rank) {
#pragma unroll
                  for (int rg = 0; rg < 4; rg++) asm volatile("st.shared.b32 [%0], %1;" ::"r"(dst + (rg & 1) * 512 + (rg >> 1) * 16), "r"(vv[rg]) : "memory");
                } else {
#pragma unroll
                  for (int rg = 0; rg < 4; rg++) st_async(dst + (rg & 1) * 512 + (rg >> 1) * 16, vv[rg], xbar);
                }
              }
            }
          }
          b ^= 1;
        }
      }
      if (lane == 0) STAMP(3, 3 + hw);
      asm volatile("bar.sync 4, 96;" ::: "memory");
      if (hw == 0 && elect_one()) { mbar_expect(BAR(B_XT), 10240); bulk_ld(sb + OFF_F2F, P.img, 10240, BAR(B_XT)); }
      mbar_wait(BAR(B_XRAW), 0);
#pragma unroll 1
      for (int n = 0; n < 6; n++) {
        const bool isH = n >= 3;
        const int c = isH ? hw + 3 * n - 9 : hw + 3 * n;
        if (c < 8) {
          int ln;
          asm volatile("mov.u32 %0, %%laneid;" : "=r"(ln));
          uint8_t* dst = smem + (isH ? OFF_H + (c & 2) * 8192 + (c >> 2) * 8192 + (c & 1) * 4096 : OFF_XT + c * XT_STRIDE) + ((ln >> 4) * 512 + (ln & 15) * 16);
          const uint8_t* src0 = isH ? (const uint8_t*)P.h + (blockIdx.x * 8 + c) * 4096 + ((ln & 15) * 32 + (ln & 16)) : dst;
          const uint8_t* src1 = src0 + (isH ? 512 : 256);
          uint32_t v[32];
#pragma unroll
          for (int i = 0; i < 8; i++) {
            const uint4 u = *(const uint4*)(((i & 1) ? src1 : src0) + (i >> 1) * 1024);
            v[4 * i] = u.x; v[4 * i + 1] = u.y; v[4 * i + 2] = u.z; v[4 * i + 3] = u.w;
          }
          const int e = normalise(v, (isH && ln == 0) ? *(const float*)(smem + OFF_D + 4 * c) : 0.f);
          if (isH) {
            mbar_wait(BAR(B_XT), 0);
            if (ln < 2) st_async(mapa(sb + OFF_SCALE + (8 * rank + c) * 4, ln), min(max(e + smem[OFF_EX + c] - 124, 1), 254) << 23, mapa(BAR(B_Y), ln));
            mbar_wait(BAR(B_SFREE), 0);
          } else if (ln == 0) smem[OFF_EX + c] = e;
#pragma unroll
          for (int i = 0; i < 8; i++)
            *(uint4*)(dst + (i >> 1) * 1024 + (i & 1) * 256) = make_uint4(v[4 * i], v[4 * i + 1], v[4 * i + 2], v[4 * i + 3]);
          if (n < 2 && elect_one()) {
            if (n == 0) mbar_expect(sbar, 4096);
            tma3d(sb + OFF_STG + 2048 * c, &P.tmQ, 16 * cl, 64 * rank, 2 * c, sbar);
          }
        }
        if (n == 2 || n == 5) {
          fence_async();
          __syncwarp();
          if (lane == 0) { mbar_arrive(BAR(isH ? B_H : B_XT)); STAMP(3, (isH ? 16 : 13) + hw); }
        }
      }
      mbar_wait(BAR(B_PKFREE), 0);
      if (hw == 0 && lane == 0) STAMP(3, 19);
      if (PD1) __nanosleep(PD1);
      {
        const int pi = hw < 2 ? 64 * mb - 288 + tid : 512 + 2 * mb + (lane & 1);
        const float* psrc = P.part + hp * 8 * 2176 + 4 * pi;
        uint4 f[8];
#pragma unroll
        for (int p = 0; p < 8; p++) f[p] = ld_rlx4(psrc + p * 2176);
        if (!opaque_true()) __trap();
#pragma unroll 1
        for (int n = 0; __any_sync(~0u, stale8(f, tag) & 1); n++) {
#pragma unroll
          for (int p = 0; p < 8; p++) ld_stale4(f[p], psrc + p * 2176, tag);
          if (n > SPIN_LIMIT) __trap();
        }
        float s0 = 0.f, s1 = 0.f, s2 = 0.f, s3 = 0.f;
#pragma unroll
        for (int p = 0; p < 8; p++) { s0 += __uint_as_float(f[p].x); s1 += __uint_as_float(f[p].y); s2 += __uint_as_float(f[p].z); s3 += __uint_as_float(f[p].w); }
        if (hw < 2 || lane < 2) st_tag4(P.kv + hp * 2176 + (4 * pi), s0, s1, s2, s3, tag);
      }
      if (lane == 0 && hw == 0) STAMP(3, 8);
      if (hw == 2) {
        unsigned* cnt = P.ocnt + (2 * mb + lane) * 32;
#pragma unroll 1
        for (int hh = 0; hh < 2; hh++) {
          mbar_wait(BAR(hh ? B_ODONE1 : B_ODONE), 0);
          if (lane < 2) asm volatile("red.release.gpu.global.add.u32 [%0], 1;" ::"l"(cnt + hh * 512) : "memory");
          if (lane == 0) STAMP(3, hh ? 6 : 7);
        }
        poll_ge(&P.ocnt[512 + rb * 32], 16 * (epoch + 1));
        asm volatile("fence.proxy.async.global;" ::: "memory");
        if (lane == 0) { mbar_arrive(BAR(B_O1RDY)); STAMP(2, 4); }
        __syncwarp();
      } else {
        if (PD2) __nanosleep(PD2);
        const int t = tid - 288;
        uint4 f[8];
        const float* src = P.kv + hp * 2176 + (4 * t);
        const float* zsrc = P.kv + hp * 2176 + (2048 + (t & 48) + 2 * (lane & 6));
        uint4 zp = ld_rlx4(zsrc);
#pragma unroll
        for (int p = 0; p < 8; p++) f[p] = ld_rlx4(src + 4 * ((p & 3) * 128 + (p >> 2) * 64));
        if (!opaque_true()) __trap();
#pragma unroll 1
        for (int n = 0; __any_sync(~0u, (stale8(f, tag) | (zp.x ^ tag)) & 1); n++) {
          ld_stale4(zp, zsrc, tag);
#pragma unroll
          for (int p = 0; p < 8; p++) ld_stale4(f[p], src + 4 * ((p & 3) * 128 + (p >> 2) * 64), tag);
          if (n > SPIN_LIMIT) __trap();
        }
#define PK2U(a, b) pk2(__uint_as_float(a), __uint_as_float(b))
        const uint32_t zf = (lane & 1) ? ((lane & 8) ? zp.w : zp.z) : ((lane & 8) ? zp.y : zp.x);
        const uint32_t zz = PK2U(zf, zf);
        *(uint4*)(smem + OFF_KVB + hw * 2560 + 2048 + lane * 16) = make_uint4(zz, zz, zz, zz);
        if (!opaque_true()) __trap();
#pragma unroll
        for (int hh = 0; hh < 2; hh++) {
          const uint4* ff = &f[4 * hh];
          uint8_t* dst = smem + OFF_KVB + hh * 2560 + q * 512 + (16 * hw + g) * 16;
          *(uint4*)dst = make_uint4(PK2U(ff[0].x, ff[0].y), PK2U(ff[1].x, ff[1].y), PK2U(ff[2].x, ff[2].y), PK2U(ff[3].x, ff[3].y));
          *(uint4*)(dst + 128) = make_uint4(PK2U(ff[0].z, ff[0].w), PK2U(ff[1].z, ff[1].w), PK2U(ff[2].z, ff[2].w), PK2U(ff[3].z, ff[3].w));
        }
        fence_async();
        __syncwarp();
        if (lane == 0) { mbar_arrive(BAR(B_KV)); if (hw == 0) STAMP(3, 9); }
      }
#define QBUF(ci) (sb + 2048 * (ci) + ((ci) < 6 ? OFF_STG : (ci) < 10 ? OFF_SPARE - 6 * 2048 : OFF_F2F - 10 * 2048))
      mbar_wait(BAR(B_Y), 0);
      if (elect_one()) {
        mbar_expect(sbar + 8, 4096);
#pragma unroll 1
        for (int ci = hw ? hw + 9 : 12; ci < 16; ci += 3) tma3d(QBUF(ci), &P.tmQ, 16 * cl, 64 * rank + 32, 2 * (ci & 7), sbar + 8);
      }
      mbar_wait(BAR(B_Q), 0);
      {
        const float2 sc0 = *(const float2*)(smem + OFF_SCALE + 8 * q), sc1 = *(const float2*)(smem + OFF_SCALE + 32 + 8 * q);
        const uint32_t yl = sb + OFF_XT + (lane & 7) * XT_STRIDE + (lane >> 3) * 16;
#pragma unroll 1
        for (int ci = hw; ci < 16; ci += 3) {
          const uint32_t qb = QBUF(ci);
          const int b = ci >= 10;
          mbar_wait(sbar + 8 * b, (ph >> b) & 1);
#pragma unroll 1
          for (int nl = 0; nl < 2; nl++) {
            uint32_t yy[2][4], qq[2][4];
            const uint32_t qa = qb + lane * 32 + ((lane & 4) << 2) + nl * 1024;
#pragma unroll
            for (int cg = 0; cg < 2; cg++) { ldsm4t(yy[cg], yl + cg * 2048 + (2 * ci + nl) * 64); ldsm4(qq[cg], qa ^ (cg * 16)); }
#pragma unroll
            for (int cg = 0; cg < 2; cg++) {
              const float2 sc = cg ? sc1 : sc0;
#pragma unroll
              for (int m = 0; m < 4; m++) {
                const float2 f = __half22float2(*(const __half2*)&yy[cg][m]);
                qq[cg][m] = hmul(qq[cg][m], pk2(f.x * sc.x, f.y * sc.y));
              }
              stsm4(qa ^ (cg * 16), qq[cg][0], qq[cg][1], qq[cg][2], qq[cg][3]);
            }
          }
          fence_async();
          __syncwarp();
          if (elect_one()) tma3d_st(&P.tmOA, qb, 16 * cl, 64 * rank + 32 * (ci >> 3), 2 * (ci & 7));
        }
        asm volatile("cp.async.bulk.commit_group;\ncp.async.bulk.wait_group.read 0;" ::: "memory");
      }
      if (lane == 0) STAMP(3, 10 + hw);
    }
  }
}

typedef CUresult (*EncodeFn)(CUtensorMap*, CUtensorMapDataType, cuuint32_t, void*, const cuuint64_t*, const cuuint64_t*,
                             const cuuint32_t*, const cuuint32_t*, CUtensorMapInterleave, CUtensorMapSwizzle,
                             CUtensorMapL2promotion, CUtensorMapFloatOOBfill);

static void enc(EncodeFn fn, CUtensorMap* m, const void* p, int rank, const cuuint64_t* dims, const cuuint64_t* strides,
                const cuuint32_t* box, CUtensorMapSwizzle swz, CUtensorMapL2promotion promo) {
  cuuint32_t es[4] = {1, 1, 1, 1};
  fn(m, CU_TENSOR_MAP_DATA_TYPE_BFLOAT16, rank, (void*)p, dims, strides, box, es, CU_TENSOR_MAP_INTERLEAVE_NONE, swz, promo,
     CU_TENSOR_MAP_FLOAT_OOB_FILL_NONE);
}

extern "C" void kernel_launch(void* const* d_in, const int* in_sizes, int n_in, void* d_out, int out_size) {
  void* fp = nullptr;
  cudaDriverEntryPointQueryResult qr;
  cudaGetDriverEntryPoint("cuTensorMapEncodeTiled", &fp, cudaEnableDefault, &qr);
  EncodeFn fn = (EncodeFn)fp;
  Params P;
  P.shift_k = (const __nv_bfloat16*)d_in[3]; P.h = (const __nv_bfloat16*)d_in[4]; P.D = (const __nv_bfloat16*)d_in[5];
  P.q = (const __nv_bfloat16*)d_in[0];
  cudaGetSymbolAddress((void**)&P.part, g_part); cudaGetSymbolAddress((void**)&P.kv, g_kv); cudaGetSymbolAddress((void**)&P.o, g_o);
  cudaGetSymbolAddress((void**)&P.ocnt, g_ocnt); cudaGetSymbolAddress((void**)&P.epoch, g_epoch);
  cudaGetSymbolAddress((void**)&P.thr, c_thr); cudaGetSymbolAddress((void**)&P.img, c_img);
  P.x = (const __nv_bfloat16*)d_in[6]; P.w = (const __nv_bfloat16*)d_in[7]; P.wo = (const __nv_bfloat16*)d_in[8];
  const CUtensorMapSwizzle S128 = CU_TENSOR_MAP_SWIZZLE_128B, S32 = CU_TENSOR_MAP_SWIZZLE_32B;
  const CUtensorMapL2promotion P0 = CU_TENSOR_MAP_L2_PROMOTION_NONE, P128 = CU_TENSOR_MAP_L2_PROMOTION_L2_128B;
  { cuuint64_t d[2] = {1024, 2048}, s[1] = {2048}; cuuint32_t b[2] = {64, 128}; enc(fn, &P.tmX, d_in[6], 2, d, s, b, S128, P128); }
  { cuuint64_t d[3] = {1024, 1024, 3}, s[2] = {6144, 2048}; cuuint32_t b[3] = {64, 64, 3}; enc(fn, &P.tmW, d_in[7], 3, d, s, b, S128, P128); }
  { cuuint64_t d[4] = {64, 64, 16, 16}, s[3] = {2048, 131072, 128}; cuuint32_t b[4] = {64, 32, 2, 2}; enc(fn, &P.tmWo, d_in[8], 4, d, s, b, S128, P128); }
  { cuuint64_t d[4] = {64, 64, 16, 16}, s[3] = {2048, 131072, 128}; cuuint32_t b[4] = {64, 32, 2, 1}; enc(fn, &P.tmWo1, d_in[8], 4, d, s, b, S128, P128); }
  { cuuint64_t d[2] = {1024, 2048}, s[1] = {2048}; cuuint32_t b[2] = {16, 72}; enc(fn, &P.tmK, d_in[1], 2, d, s, b, S32, PKV); }
  { cuuint64_t d[2] = {1024, 2048}, s[1] = {2048}; cuuint32_t b[2] = {16, 64}; enc(fn, &P.tmV, d_in[2], 2, d, s, b, S32, PKV); }
  { cuuint64_t d[3] = {1024, 128, 16}, s[2] = {32768, 2048}; cuuint32_t b[3] = {16, 32, 2}; enc(fn, &P.tmQ, d_in[0], 3, d, s, b, S32, PKV); }
  { cuuint64_t d[3] = {1024, 128, 16}, s[2] = {65536, 4096}; cuuint32_t b[3] = {16, 32, 2}; enc(fn, &P.tmOA, d_out, 3, d, s, b, S32, P0); }
  { cuuint64_t d[2] = {2048, 2048}, s[1] = {4096}; cuuint32_t b[2] = {64, 64}; enc(fn, &P.tmOB, d_out, 2, d, s, b, S128, P0); }
  cudaFuncSetAttribute(fused_kernel, cudaFuncAttributeMaxDynamicSharedMemorySize, SMEM_TOTAL);
  fused_kernel<<<128, 384, SMEM_TOTAL>>>(P);
}
```

```cpp
#include <cuda_runtime.h>
#include <cuda_bf16.h>
#include <cuda_fp16.h>
#include <cuda.h>
#include <stdint.h>

template<int TA, int TB, int SA=1> __device__ __forceinline__ void wgmma_ss_n192(float (&d)[96], uint64_t da, uint64_t db, int scale_d) {
  asm volatile("{\n.reg .pred p;\nsetp.ne.b32 p, %98, 0;\n"
    "wgmma.mma_async.sync.aligned.m64n192k16.f32.bf16.bf16 {%0, %1, %2, %3, %4, %5, %6, %7, %8, %9, %10, %11, %12, %13, %14, %15, %16, %17, %18, %19, %20, %21, %22, %23, %24, %25, %26, %27, %28, %29, %30, %31, %32, %33, %34, %35, %36, %37, %38, %39, %40, %41, %42, %43, %44, %45, %46, %47, %48, %49, %50, %51, %52, %53, %54, %55, %56, %57, %58, %59, %60, %61, %62, %63, %64, %65, %66, %67, %68, %69, %70, %71, %72, %73, %74, %75, %76, %77, %78, %79, %80, %81, %82, %83, %84, %85, %86, %87, %88, %89, %90, %91, %92, %93, %94, %95}, %96, %97, p, %101, 1, %99, %100;\n}\n"
    : "+f"(d[0]), "+f"(d[1]), "+f"(d[2]), "+f"(d[3]), "+f"(d[4]), "+f"(d[5]), "+f"(d[6]), "+f"(d[7]), "+f"(d[8]), "+f"(d[9]), "+f"(d[10]), "+f"(d[11]), "+f"(d[12]), "+f"(d[13]), "+f"(d[14]), "+f"(d[15]), "+f"(d[16]), "+f"(d[17]), "+f"(d[18]), "+f"(d[19]), "+f"(d[20]), "+f"(d[21]), "+f"(d[22]), "+f"(d[23]), "+f"(d[24]), "+f"(d[25]), "+f"(d[26]), "+f"(d[27]), "+f"(d[28]), "+f"(d[29]), "+f"(d[30]), "+f"(d[31]), "+f"(d[32]), "+f"(d[33]), "+f"(d[34]), "+f"(d[35]), "+f"(d[36]), "+f"(d[37]), "+f"(d[38]), "+f"(d[39]), "+f"(d[40]), "+f"(d[41]), "+f"(d[42]), "+f"(d[43]), "+f"(d[44]), "+f"(d[45]), "+f"(d[46]), "+f"(d[47]), "+f"(d[48]), "+f"(d[49]), "+f"(d[50]), "+f"(d[51]), "+f"(d[52]), "+f"(d[53]), "+f"(d[54]), "+f"(d[55]), "+f"(d[56]), "+f"(d[57]), "+f"(d[58]), "+f"(d[59]), "+f"(d[60]), "+f"(d[61]), "+f"(d[62]), "+f"(d[63]), "+f"(d[64]), "+f"(d[65]), "+f"(d[66]), "+f"(d[67]), "+f"(d[68]), "+f"(d[69]), "+f"(d[70]), "+f"(d[71]), "+f"(d[72]), "+f"(d[73]), "+f"(d[74]), "+f"(d[75]), "+f"(d[76]), "+f"(d[77]), "+f"(d[78]), "+f"(d[79]), "+f"(d[80]), "+f"(d[81]), "+f"(d[82]), "+f"(d[83]), "+f"(d[84]), "+f"(d[85]), "+f"(d[86]), "+f"(d[87]), "+f"(d[88]), "+f"(d[89]), "+f"(d[90]), "+f"(d[91]), "+f"(d[92]), "+f"(d[93]), "+f"(d[94]), "+f"(d[95])
    : "l"(da), "l"(db), "r"(scale_d), "n"(TA), "n"(TB), "n"(SA));
}
template<int TA, int TB, int SA=1> __device__ __forceinline__ void wgmma_ss_n128(float (&d)[64], uint64_t da, uint64_t db, int scale_d) {
  asm volatile("{\n.reg .pred p;\nsetp.ne.b32 p, %66, 0;\n"
    "wgmma.mma_async.sync.aligned.m64n128k16.f32.bf16.bf16 {%0, %1, %2, %3, %4, %5, %6, %7, %8, %9, %10, %11, %12, %13, %14, %15, %16, %17, %18, %19, %20, %21, %22, %23, %24, %25, %26, %27, %28, %29, %30, %31, %32, %33, %34, %35, %36, %37, %38, %39, %40, %41, %42, %43, %44, %45, %46, %47, %48, %49, %50, %51, %52, %53, %54, %55, %56, %57, %58, %59, %60, %61, %62, %63}, %64, %65, p, %69, 1, %67, %68;\n}\n"
    : "+f"(d[0]), "+f"(d[1]), "+f"(d[2]), "+f"(d[3]), "+f"(d[4]), "+f"(d[5]), "+f"(d[6]), "+f"(d[7]), "+f"(d[8]), "+f"(d[9]), "+f"(d[10]), "+f"(d[11]), "+f"(d[12]), "+f"(d[13]), "+f"(d[14]), "+f"(d[15]), "+f"(d[16]), "+f"(d[17]), "+f"(d[18]), "+f"(d[19]), "+f"(d[20]), "+f"(d[21]), "+f"(d[22]), "+f"(d[23]), "+f"(d[24]), "+f"(d[25]), "+f"(d[26]), "+f"(d[27]), "+f"(d[28]), "+f"(d[29]), "+f"(d[30]), "+f"(d[31]), "+f"(d[32]), "+f"(d[33]), "+f"(d[34]), "+f"(d[35]), "+f"(d[36]), "+f"(d[37]), "+f"(d[38]), "+f"(d[39]), "+f"(d[40]), "+f"(d[41]), "+f"(d[42]), "+f"(d[43]), "+f"(d[44]), "+f"(d[45]), "+f"(d[46]), "+f"(d[47]), "+f"(d[48]), "+f"(d[49]), "+f"(d[50]), "+f"(d[51]), "+f"(d[52]), "+f"(d[53]), "+f"(d[54]), "+f"(d[55]), "+f"(d[56]), "+f"(d[57]), "+f"(d[58]), "+f"(d[59]), "+f"(d[60]), "+f"(d[61]), "+f"(d[62]), "+f"(d[63])
    : "l"(da), "l"(db), "r"(scale_d), "n"(TA), "n"(TB), "n"(SA));
}
template<int TA, int TB, int SA=1> __device__ __forceinline__ void wgmma_ss_n72(float (&d)[36], uint64_t da, uint64_t db, int scale_d) {
  asm volatile("{\n.reg .pred p;\nsetp.ne.b32 p, %38, 0;\n"
    "wgmma.mma_async.sync.aligned.m64n72k16.f32.bf16.bf16 {%0, %1, %2, %3, %4, %5, %6, %7, %8, %9, %10, %11, %12, %13, %14, %15, %16, %17, %18, %19, %20, %21, %22, %23, %24, %25, %26, %27, %28, %29, %30, %31, %32, %33, %34, %35}, %36, %37, p, %41, 1, %39, %40;\n}\n"
    : "+f"(d[0]), "+f"(d[1]), "+f"(d[2]), "+f"(d[3]), "+f"(d[4]), "+f"(d[5]), "+f"(d[6]), "+f"(d[7]), "+f"(d[8]), "+f"(d[9]), "+f"(d[10]), "+f"(d[11]), "+f"(d[12]), "+f"(d[13]), "+f"(d[14]), "+f"(d[15]), "+f"(d[16]), "+f"(d[17]), "+f"(d[18]), "+f"(d[19]), "+f"(d[20]), "+f"(d[21]), "+f"(d[22]), "+f"(d[23]), "+f"(d[24]), "+f"(d[25]), "+f"(d[26]), "+f"(d[27]), "+f"(d[28]), "+f"(d[29]), "+f"(d[30]), "+f"(d[31]), "+f"(d[32]), "+f"(d[33]), "+f"(d[34]), "+f"(d[35])
    : "l"(da), "l"(db), "r"(scale_d), "n"(TA), "n"(TB), "n"(SA));
}
template<int TB, int SA=1> __device__ __forceinline__ void wgmma_rs_n40(float (&d)[20], uint32_t a0, uint32_t a1, uint32_t a2, uint32_t a3, uint64_t db, int scale_d) {
  asm volatile("{\n.reg .pred p;\nsetp.ne.b32 p, %25, 0;\n"
    "wgmma.mma_async.sync.aligned.m64n40k16.f32.bf16.bf16 {%0, %1, %2, %3, %4, %5, %6, %7, %8, %9, %10, %11, %12, %13, %14, %15, %16, %17, %18, %19}, {%20, %21, %22, %23}, %24, p, %27, 1, %26;\n}\n"
    : "+f"(d[0]), "+f"(d[1]), "+f"(d[2]), "+f"(d[3]), "+f"(d[4]), "+f"(d[5]), "+f"(d[6]), "+f"(d[7]), "+f"(d[8]), "+f"(d[9]), "+f"(d[10]), "+f"(d[11]), "+f"(d[12]), "+f"(d[13]), "+f"(d[14]), "+f"(d[15]), "+f"(d[16]), "+f"(d[17]), "+f"(d[18]), "+f"(d[19])
    : "r"(a0), "r"(a1), "r"(a2), "r"(a3), "l"(db), "r"(scale_d), "n"(TB), "n"(SA));
}
template<int TB> __device__ __forceinline__ void wgmma_hrs_n64(uint32_t (&d)[16], uint32_t a0, uint32_t a1, uint32_t a2, uint32_t a3, uint64_t db, int scale_d) {
  asm volatile("{\n.reg .pred p;\nsetp.ne.b32 p, %21, 0;\n"
    "wgmma.mma_async.sync.aligned.m64n64k16.f16.f16.f16 {%0, %1, %2, %3, %4, %5, %6, %7, %8, %9, %10, %11, %12, %13, %14, %15}, {%16, %17, %18, %19}, %20, p, 1, 1, %22;\n}\n"
    : "+r"(d[0]), "+r"(d[1]), "+r"(d[2]), "+r"(d[3]), "+r"(d[4]), "+r"(d[5]), "+r"(d[6]), "+r"(d[7]), "+r"(d[8]), "+r"(d[9]), "+r"(d[10]), "+r"(d[11]), "+r"(d[12]), "+r"(d[13]), "+r"(d[14]), "+r"(d[15])
    : "r"(a0), "r"(a1), "r"(a2), "r"(a3), "l"(db), "r"(scale_d), "n"(TB));
}
template<int TB> __device__ __forceinline__ void wgmma_hrs_n32(uint32_t (&d)[8], uint32_t a0, uint32_t a1, uint32_t a2, uint32_t a3, uint64_t db, int scale_d) {
  asm volatile("{\n.reg .pred p;\nsetp.ne.b32 p, %13, 0;\n"
    "wgmma.mma_async.sync.aligned.m64n32k16.f16.f16.f16 {%0, %1, %2, %3, %4, %5, %6, %7}, {%8, %9, %10, %11}, %12, p, 1, 1, %14;\n}\n"
    : "+r"(d[0]), "+r"(d[1]), "+r"(d[2]), "+r"(d[3]), "+r"(d[4]), "+r"(d[5]), "+r"(d[6]), "+r"(d[7])
    : "r"(a0), "r"(a1), "r"(a2), "r"(a3), "l"(db), "r"(scale_d), "n"(TB));
}

__device__ __align__(128) const uint32_t c_thr[1536] = {
  0x33fb33ff,0xa49c9de4,0x33273352,0xaf2cae76,0x33e233f1,0xa96ca7bd,0x32c432f7,0xb045afdd,0x33b733cf,0xac3eaaf7,0x3250328c,0xb0eab099,
  0x3378339a,0xadbcacff,0x31cd3211,0xb182b137,0x33d033fb,0xaadea46a,0x299e2d17,0xb3e0b396,0x32fb337a,0xafd2adb1,0xa78b1f76,0xb3f2b3ff,
  0x318b3254,0xb1c5b0e5,0xae6bac32,0xb354b3b8,0x2f4230a3,0xb321b285,0xb133b040,0xb215b2c7,0x337c33f2,0xada5a759,0xb179afc8,0xb1d6b2fe,
  0x31463293,0xb204b08e,0xb394b2ba,0xad23b055,0x2b402f4e,0xb3cbb31e,0xb3e4b3f9,0x293ba533,0xac269c52,0xb3bab400,0xb258b357,0x30e02e5f,
  0x330133e5,0xafbda922,0xb3f3b3c9,0x2727ab59,0x2deb314a,0xb36fb200,0xb194b32f,0x31bc2f0a,0xacdb2084,0xb39fb3ff,0xa565aea4,0x33f93347,
  0xb2b6b0db,0xb05ab25c,0x30892c1a,0x329733bc,0x326033d4,0xb0d6aa94,0xb00ab29b,0x32e83084,0x20e82f64,0xb3feb318,0x2d8da597,0x338133f8,
  0xb1fcae48,0xb14fb35c,0x339031b8,0x2d3a3199,0xb3e6b3ae,0x2909ac7b,0x32d133f4,0xb030a6f5,0x319d33bf,0xb1b3ac02,0x2e3ca874,0x335e33ec,
  0xacc32b89,0xb3a3b3c6,0x33f83276,0x25c930b7,0xb3dcb1f8,0xaa01b154,0x30653335,0xb2b0aef4,0xb107b383,0x32392d81,0xafa6214d,0xb307b3fe,
  0x30bc33a5,0xb273acb7,0x33c5311b,0x2ba23229,0xb0cc94b6,0xb267b400,0x30153360,0xb2e1ae31,0xb385b3ab,0x2d76ac93,0xb166a691,0xb1e7b3f5,
  0x22deb06a,0x33fd32ac,0xb337b3da,0x2ee8aa19,0x2f853387,0xb310ad6a,0x322d33fe,0xb1162216,0xb2a9abd3,0xb06fb3c2,0xb07428a6,0xb2a5b3ea,
  0xb111b3e9,0x323128be,0xb30db3c3,0x2f90abba,0x31aa227a,0x31a633fd,0x2e25ad5e,0x33633389,0x2d6a3365,0xb387ae1a,0xa21631aa,0xb3feb1a6,
  0xb3c2af85,0xabd3b310,0xb3eab22d,0x28a6b116,0xa8beb2a9,0x33e9306f,0x2bbab074,0x33c332a5,0x33fd3111,0x227a3231,0x3389330d,0xad5e2f90,
  0x2a63333f,0xb3d7aec6,0xb2a2a1b1,0xb07ab3fe,0xb3f7b158,0x25fbb1f4,0xacb7b38b,0x33a52d52,0x2e0eb025,0x336832d8,0x340030bc,0x14b63273,
  0x323533c0,0xb10c2beb,0xac9330cc,0xb3abb267,0x23433316,0xb3fdaf6f,0xb38eb225,0x2d46b11f,0xb342b29e,0x2ebbb07f,0x31e3aa7c,0x316b33d6,
  0x3264a6c3,0x30d133f5,0x2c0233ac,0xb3bfac87,0x28f0336a,0xb3e7ae02,0xb3c6b19d,0x2b89b1b3,0xa59732e8,0xb3f8b00a,0xaccfb3ed,0x33a1285b,
  0xb1b8b381,0x3199ad8d,0x336c31df,0xadf73170,0x33f42d3a,0x26f53390,0xb30423a7,0xafb2b3fc,0xb05f3030,0xb2b3b2d1,0x29e8b27a,0x33dd30b2,
  0xab5932b6,0xb3c9b05a,0x30adb089,0x327e3297,0xaf0ab3f3,0x332fa727,0x240633b0,0xb3fcac6f,0x33473194,0xaea431bc,0xb174b359,0x31daae54,
  0xb3bca565,0xac1ab3f9,0x33ee2f59,0xa842331b,0xaddf3281,0xb371b0a8,0x34002b40,0x1c5233cb,0xa759b3ef,0x33f22829,0xb2fe2c26,0xafc8b3ba,
  0x308e337c,0xb2932da5,0x3055b179,0x32ba31d6,0xb31eb146,0x2f4eb204,0xa5333394,0xb3f9ad23,0xaff33249,0xb2f1b0f3,0x30e532fb,0xb2542fd2,
  0x2b28b373,0x33cc2dd4,0xb285b18b,0x30a3b1c5,0x246a33fa,0xb3fba500,0x33962f42,0xad173321,0xadb1b3d0,0x337aaade,0xb3ffa99e,0x1f76b3e0,
  0xb0ee320d,0xb24db13c,0xac4b3398,0xb3b5ad0b,0x304ab289,0x32c1309e,0x2985b3ce,0x33e12b0f,0xaf3732f4,0xb324afe8,0xa4ce33f0,0xb3faa7ef,
  0x2dc8b34f,0x33762e82,0x9de4b3ff,0x33ff1ead,0xb1c931cd,0xb186b182,0xb3762e82,0xadc8b34f,0x324db13c,0x30ee320d,0x33b5ad0b,0x2c4b3398,
  0xb2c1309e,0xb04ab289,0xb3e12b0f,0xa985b3ce,0x3324afe8,0x2f3732f4,0x33faa7ef,0x24ce33f0,0xb285318b,0xb0a3b1c5,0xb2c7ae6b,0x3040b354,
  0x3396af42,0x2d173321,0x31413133,0xb2093215,0xb3ff299e,0x9f76b3e0,0xae8db2bd,0x334cb050,0x33b8278b,0xac3233f2,0x281033b3,0xb3ef2c57,
  0xb31e3146,0xaf4eb204,0xa533b394,0x33f9ad23,0x3400ab40,0x9c5233cb,0xae5f33e4,0xb357a93b,0xb2feac26,0x2fc8b3ba,0x3245b258,0x30f830e0,
  0x30553179,0xb2ba31d6,0xb3df2e99,0xa9b6b34a,0xb39230fd,0xad2fb241,0x3200b301,0x314a2fbd,0x337f1b11,0xad993400,0xb3ff2deb,0xa084b36f,
  0xb005b129,0x32ebb21d,0x325c2cdb,0xb0db339f,0xa92233de,0xb3e529cf,0xab59b2b6,0x33c9b05a,0xb3dd30b2,0xa9e8b27a,0x33d4ab71,0xaa9433c8,
  0x32212c0e,0xb12433bd,0xaf64b0d6,0x3318b260,0x197fb345,0x3400aeaf,0xae4833fe,0xb35c20e8,0xb23d3332,0xb102aeff,0x33aeb14f,0x2c7b31fc,
  0xb3fe3065,0xa14db2b0,0x2ebb307f,0xb342329e,0x300f2fa6,0xb2e53307,0x30d1b3f5,0x326426c3,0x302ab400,0x32d517db,0xb3e72e02,0x28f0b36a,
  0xb3fd2f6f,0x2343b316,0x2d46311f,0xb38e3225,0xb3f53015,0x2691b2e1,0xaf9b33eb,0xb30a288d,0x2a193166,0xb3da31e7,0x33d7aec6,0xaa63333f,
  0x3313b337,0x2f7a2ee8,0xa5fbb1f4,0x33f7b158,0xb1a1a8d7,0x31afb3e8,0xb36832d8,0xae0eb025,0xb3c22f85,0x2bd3b310,0xb3ea322d,0xa8a6b116,
  0xa8be32a9,0xb3e9306f,0x2bba3074,0xb3c332a5,0x33fdb111,0xa27a3231,0x3389b30d,0x2d5e2f90,0xa216b1aa,0x33feb1a6,0xaed2ae25,0x333db363,
  0xb3652edd,0x2e1ab33a,0xb1aa227a,0x31a6b3fd,0xaf853387,0xb3102d6a,0xb22d33fe,0xb116a216,0x32a9abd3,0xb06f33c2,0x307428a6,0xb2a533ea,
  0x3111b3e9,0x3231a8be,0x330db3c3,0x2f902bba,0xb2e12e31,0x3015b360,0x288db1a1,0x33ebb1af,0xb1e733f5,0xb1662691,0xb33f2f9b,0x2ec6b30a,
  0x2ee82a19,0xb33733da,0xb15833d7,0xb1f42a63,0x33e8b313,0x28d72f7a,0x302525fb,0xb2d833f7,0xb2392d81,0x3107b383,0x3307b3fe,0x2fa6214d,
  0xb35e33ec,0xae3ca874,0x97dbb00f,0x3400b2e5,0xa5c930b7,0xb3f83276,0xb316302a,0x2f6fb2d5,0x32b0aef4,0xb0653335,0xb29e33fd,0xb07f2343,
  0xb1702ccf,0x31dfb3a1,0x3345b124,0xaeaf3221,0xb3fc336c,0xa3a7adf7,0x3332b400,0x2eff997f,0xb0b23304,0xb27a2fb2,0x2b71b102,0x33c8b23d,
  0x2c0e29e8,0xb3bd33dd,0xb0d62a94,0x3260b3d4,0xb0892c1a,0x3297b3bc,0x2aad2842,0xb3d333ee,0xb3b0327e,0x2c6fb0ad,0x3241b035,0xb0fd32ce,
  0xb35933fc,0xae542406,0x3400b392,0x1b112d2f,0xaf5931da,0xb31b3174,0x321db37f,0x3129ad99,0xaf152ac6,0x332cb3d2,0xb1463293,0xb204308e,
  0xb281312e,0x30a8b219,0xab402f4e,0xb3cb331e,0xb3ef3371,0x2829addf,0x2c269c52,0xb3ba3400,0xb37c33f2,0xada52759,0x3179afc8,0xb1d632fe,
  0xacf32953,0x339cb3e3,0xb3fa33cc,0x2500ab28,0xb0942f21,0x3290b32a,0xb3d033fb,0xaade246a,0xb249317d,0x30f3b1d2,0xb2fb337a,0xafd22db1,
  0xb37332f1,0x2dd4aff3,0xb18b3254,0xb1c530e5,0xa96c27bd,0x33e2b3f1,0xb0452fdd,0x32c4b2f7,0xac3e2af7,0x33b7b3cf,0xb0ea3099,0x3250b28c,
  0xadbc2cff,0x3378b39a,0xb1823137,0x31cdb211,0xaf2c2e76,0x3327b352,0xb20d31c9,0x313cb186,0x313c3186,0xb20db1c9,0x2d0b2dc8,0xb398b376,
  0x309e30ee,0xb289b24d,0x2b0f2c4b,0xb3ceb3b5,0x2fe8304a,0xb2f4b2c1,0x27ef2985,0xb3f0b3e1,0x2e822f37,0xb34fb324,0x1ead24ce,0xb3ffb3fa,
  0xb2bdb209,0xb050b141,0xb290b32a,0x30942f21,0xb3b3b34c,0xac57ae8d,0xb0f3b1d2,0x3249317d,0xb400b3ef,0x1d1ba810,0xadd4aff3,0x337332f1,
  0xb39cb3e3,0x2cf32953,0xa500ab28,0x33fa33cc,0xae99b0f8,0x334a3245,0x33ff33b2,0x201f2c63,0x2438a9b6,0x33fc33df,0x332c33d2,0xaf15aac6,
  0x303a2ce7,0x32cb339e,0x30a83219,0xb281b12e,0x32ee31c0,0x2ffe3190,0x28292ddf,0xb3efb371,0x33b0327e,0x2c6f30ad,0xb241b035,0xb0fdb2ce,
  0x335933fc,0xae54a406,0xb400b392,0x1b11ad2f,0x2f5931da,0xb31bb174,0xb21db37f,0x31292d99,0xaaad2842,0xb3d3b3ee,0xa9cfb005,0x33de32eb,
  0x285b305f,0xb3edb2b3,0x2c0ea9e8,0x33bd33dd,0xb170accf,0xb1dfb3a1,0x33453124,0x2eaf3221,0xb3fcb36c,0x23a7adf7,0x33323400,0xaeff997f,
  0xb0b2b304,0x327a2fb2,0x2b713102,0xb3c8b23d,0xb400b2e5,0x17dbb00f,0x2e023264,0xb36ab0d1,0xaf6fb2d5,0x3316302a,0xb11fa8f0,0xb225b3e7,
  0x307f2343,0x329e33fd,0xb3d6b38e,0x2a7cad46,0x33f53342,0xa6c32ebb,0xac87b1e3,0x33ac316b,0x28d7af7a,0x33e83313,0xb2d8b3f7,0x3025a5fb,
  0x33eb31af,0x288d31a1,0x2bebae0e,0x33c03368,0x2ec6330a,0xb33faf9b,0x33fe3235,0x21b1310c,0xb1f4aa63,0xb158b3d7,0x2d5232a2,0xb38bb07a,
  0x33a7333d,0xacab2ed2,0x33f63162,0x262d31eb,0xaa4b301a,0xb3d8b2de,0x2a32326b,0xb3d9b0c7,0xb3f6b26f,0x265fb0c1,0xb3a9b020,0xac9fb2db,
  0x0e48b15d,0x340031f0,0xae1ab33a,0x33652edd,0xaed22e25,0xb33db363,0xb1eb0e48,0xb162b400,0xb2deb3a7,0x301aacab,0xb0c7b3f6,0x326b262d,
  0x30c1aa4b,0x326f33d8,0x32db2a32,0x302033d9,0x31f033f6,0xb15d265f,0x2edd33a9,0xb33aac9f,0xb2acb385,0x306aad76,0x2a19b166,0x33da31e7,
  0x3229a2de,0x311b33fd,0x33133337,0xaf7a2ee8,0x2e3133c5,0xb360aba2,0xb1a128d7,0xb1afb3e8,0xb3f5b015,0xa691b2e1,0xaf9bb3eb,0x330a288d,
  0x3154acc3,0x31f833a3,0x2ef433f8,0xb335a5c9,0x2d8133dc,0xb383aa01,0xb3feb065,0x214db2b0,0xb3ecb107,0x2874b239,0x300fafa6,0x32e53307,
  0x30b7ae3c,0x3276335e,0x302a3400,0xb2d517db,0x312433bd,0xb2212c0e,0xb318b260,0x2f64b0d6,0xb400aeaf,0x997fb345,0x335c20e8,0x2e4833fe,
  0x3102aeff,0x323d3332,0xac7b31fc,0xb3aeb14f,0x2a9433c8,0xb3d4ab71,0xb084b3e6,0x329ba909,0xb2ce2aad,0xb035b3d3,0x33e529cf,0x292233de,
  0x2d2fb241,0x339230fd,0xb14a2fbd,0xb200b301,0x2d993400,0xb37f1b11,0x2084b36f,0x33ff2deb,0xb2ebb21d,0x3005b129,0x30db339f,0xb25c2cdb,
  0xae5fb3e4,0x3357a93b,0xb190303a,0xb1c0b2cb,0x32453258,0xb0f830e0,0x2c63b2ee,0x33b22ffe,0xb3dfae99,0x29b6b34a,0x2ac633ff,0xb3d2a01f,
  0x339ea438,0x2ce733fc,0xb12eb32c,0x3219af15,0x33b8a78b,0x2c3233f2,0x2810b3b3,0x33ef2c57,0xb2c72e6b,0xb040b354,0x29533400,0xb3e31d1b,
  0x3141b133,0x32093215,0xaf21b39c,0x332aacf3,0xae8d32bd,0xb34cb050,0x317d3290,0xb1d23094,0x27bd33fb,0xb3f1249c,0x2fdd3327,0xb2f72f2c,
  0xaaf7b3e2,0x33cfa96c,0xb099b2c4,0x328cb045,0x2cff33b7,0xb39a2c3e,0x31373250,0xb21130ea,0xae76b378,0x3352adbc,0xb1c9b1cd,0x3186b182,
  0xb3ff1ead,0x1de4b3ff,0xb352adbc,0x2e76b378,0x33f1249c,0xa7bd33fb,0x32f72f2c,0xafdd3327,0xb3cfa96c,0x2af7b3e2,0xb28cb045,0x3099b2c4,
  0x339a2c3e,0xacff33b7,0x321130ea,0xb1373250,0x2953b400,0x33e31d1b,0x33ccadd4,0x2b283373,0xaf21339c,0xb32aacf3,0xb3fb2500,0x246ab3fa,
  0x317db290,0x31d23094,0x337a2ade,0xadb133d0,0xb2f130f3,0xaff3b249,0xb254afd2,0x30e5b2fb,0x339e2438,0xace733fc,0xb12e332c,0xb219af15,
  0xb190b03a,0x31c0b2cb,0x3371b0a8,0x2ddf3281,0x2c6332ee,0xb3b22ffe,0xb3f22829,0x2759b3ef,0x2ac6b3ff,0x33d2a01f,0x32932da5,0xb08e337c,
  0xaf0a33f3,0xb32fa727,0x2406b3b0,0x33fcac6f,0x3347b194,0x2ea431bc,0xb1743359,0xb1daae54,0xb3bc2565,0x2c1ab3f9,0x33eeaf59,0x2842331b,
  0x30ad3089,0xb27e3297,0xb2ceaaad,0x3035b3d3,0xb29ba909,0x3084b3e6,0x305f3030,0xb2b332d1,0x259732e8,0xb3f8300a,0x2ccfb3ed,0x33a1a85b,
  0x31b8b381,0x31992d8d,0xb36c31df,0xadf7b170,0xb3f42d3a,0x26f5b390,0x330423a7,0xafb233fc,0x316bb3d6,0x31e32a7c,0xb3832a01,0x2d81b3dc,
  0xb3bf2c87,0x2c02b3ac,0x28743239,0xb3ec3107,0x2b8931b3,0xb3c6319d,0x3276b35e,0x30b72e3c,0x31f8b3a3,0x31542cc3,0xb33525c9,0x2ef4b3f8,
  0x310c2beb,0xb23533c0,0x33abb267,0x2c9330cc,0x307ab3fe,0x32a2a1b1,0xb06aad76,0x32acb385,0xb3a52d52,0x2cb7b38b,0xb11b33fd,0xb229a2de,
  0x94b63273,0xb40030bc,0x3360aba2,0xae3133c5,0xb2de33a7,0xb01aacab,0xb0c733f6,0xb26b262d,0x30c12a4b,0xb26f33d8,0x32dbaa32,0xb02033d9,
  0x31f0b3f6,0x315d265f,0x2eddb3a9,0x333aac9f,0xb1eb8e48,0x3162b400,0xb3872e1a,0x2d6ab365,0xae25ad5e,0x3363b389,0x8e48b15d,0x3400b1f0,
  0xb3a7333d,0xacabaed2,0xb3f63162,0x262db1eb,0x2a4b301a,0xb3d832de,0xaa32326b,0xb3d930c7,0x33f6b26f,0x265f30c1,0x33a9b020,0xac9f32db,
  0x33c0b368,0x2beb2e0e,0x30cc94b6,0xb2673400,0x21b1b10c,0x33feb235,0x3385b3ab,0x2d762c93,0xb38b307a,0x2d52b2a2,0xa2deb06a,0x33fdb2ac,
  0xb0bc33a5,0xb2732cb7,0xb3c5311b,0x2ba2b229,0x26c32ebb,0xb3f53342,0xb3ac316b,0x2c87b1e3,0x336ab0d1,0xae023264,0xb19d33bf,0xb1b32c02,
  0x3225b3e7,0x311fa8f0,0x2cc32b89,0xb3a333c6,0xaa7cad46,0x33d6b38e,0x33dcb1f8,0xaa013154,0xb3fe3318,0x20e8af64,0x3381b3f8,0x2d8d2597,
  0xb14f335c,0xb1fc2e48,0x2d3ab199,0x3390b1b8,0x29092c7b,0xb3e633ae,0xb03026f5,0x32d1b3f4,0x32e8b084,0xb00a329b,0xb3ed32b3,0x285bb05f,
  0x29cfb005,0x33deb2eb,0xb05a325c,0xb2b630db,0xafbd2922,0x3301b3e5,0x27272b59,0xb3f333c9,0xb36f3200,0x2debb14a,0x31bcaf0a,0xb194332f,
  0xb39f33ff,0xacdba084,0x33f9b347,0xa5652ea4,0x3394b2ba,0xad233055,0xa438a9b6,0x33fcb3df,0x33e4b3f9,0x293b2533,0xb03a2ce7,0x32cbb39e,
  0x3258b357,0x30e0ae5f,0xb2ee31c0,0x2ffeb190,0x2e99b0f8,0x334ab245,0xb3ff33b2,0x201fac63,0xaf4230a3,0xb3213285,0x3133b040,0xb21532c7,
  0xa99e2d17,0xb3e03396,0x32bdb209,0xb0503141,0x278b1f76,0xb3f233ff,0x33b3b34c,0xac572e8d,0x2e6bac32,0xb35433b8,0x3400b3ef,0x1d1b2810,
  0xb289324d,0x309eb0ee,0xb3ce33b5,0x2b0fac4b,0xb2f432c1,0x2fe8b04a,0xb3f033e1,0x27efa985,0xb34f3324,0x2e82af37,0xb3ff33fa,0x1eada4ce,
  0xb3983376,0x2d0badc8,0xb3fb33ff,0xa49c1de4,0x351c35f6,0xac93a617,0xb8a3b93c,0x308d2a16,0x32f43448,0xb160afa5,0xb6a4b7fe,0x353a3389,
  0x2fa53160,0xb448b2f4,0xb389b53a,0x37fe36a4,0x26172c93,0xb5f6b51c,0xaa16b08d,0x393c38a3,0x34c3358c,0xac47a5b2,0xb85fb8f3,0x304229b1,
  0x327e33fd,0xb106af26,0xb63cb785,0x34e7330f,0x2f263106,0xb3fdb27e,0xb30fb4e7,0x3785363c,0x25b22c47,0xb58cb4c3,0xa9b1b042,0x38f3385f,
  0x346a3523,0xabf6a54d,0xb81ab8a8,0x2fef294d,0x3209336b,0xb0acaea7,0xb5d4b70a,0x34933294,0x2ea730ac,0xb36bb209,0xb294b493,0x370a35d4,
  0x254d2bf6,0xb523b46a,0xa94dafef,0x38a8381a,0x341334bc,0xab5fa4e9,0xb7a6b85a,0x2f5928e8,0x319432da,0xb052ae28,0xb56ab68d,0x343e3219,
  0x2e283052,0xb2dab194,0xb219b43e,0x368d356a,0x24e92b5f,0xb4bcb413,0xa8e8af59,0x385a37a6,0x33783456,0xaac8a484,0xb715b80a,0x2ec32884,
  0x3120324a,0xaff2ada9,0xb4ffb60e,0x33d3319e,0x2da92ff2,0xb24ab120,0xb19eb3d3,0x360e34ff,0x24842ac8,0xb456b378,0xa884aec3,0x380a3715,
  0x32cd33e3,0xaa31a420,0xb682b76f,0x2e2d281f,0x30ac31bb,0xaf3fad2a,0xb493b58d,0x33283122,0x2d2a2f3f,0xb1bbb0ac,0xb122b328,0x358d3493,
  0x24202a31,0xb3e3b2cd,0xa81fae2d,0x376f3682,0x3223331c,0xa999a376,0xb5ebb6c6,0x2d972776,0x3039312d,0xae8dacac,0xb426b50b,0x327c30a6,
  0x2cac2e8d,0xb12db039,0xb0a6b27c,0x350b3426,0x23762999,0xb31cb223,0xa776ad97,0x36c635eb,0x317a3257,0xa902a2ad,0xb552b61a,0x2d0026ad,
  0x2f8c309f,0xaddcac2e,0xb371b487,0x31cf3029,0x2c2e2ddc,0xb09faf8c,0xb029b1cf,0x34873371,0x22ad2902,0xb257b17a,0xa6adad00,0x361a3552,
  0x30d23194,0xa86ba1e4,0xb4b7b56a,0x2c6a25e4,0x2ea73012,0xad2aab5f,0xb294b402,0x31222f59,0x2b5f2d2a,0xb012aea7,0xaf59b122,0x34023294,
  0x21e4286b,0xb194b0d2,0xa5e4ac6a,0x356a34b7,0x302c30d2,0xa7a9a11b,0xb41ab4b7,0x2ba7251b,0x2dc22f0c,0xac79aa63,0xb1b6b2f7,0x30742e5f,
  0x2a632c79,0xaf0cadc2,0xae5fb074,0x32f731b6,0x211b27a9,0xb0d2b02c,0xa51baba7,0x34b7341a,0x2f0c3012,0xa67ba052,0xb2f7b402,0x2a7a2452,
  0x2cde2df5,0xab91a967,0xb0d7b1e8,0x2f8b2d65,0x29672b91,0xadf5acde,0xad65af8b,0x31e830d7,0x2052267b,0xb012af0c,0xa452aa7a,0x340232f7,
  0x2dc22ea7,0xa54d9f12,0xb1b6b294,0x294d2311,0x2bf62cde,0xaa31a86b,0xafefb0d7,0x2e2d2c6a,0x286b2a31,0xacdeabf6,0xac6aae2d,0x30d72fef,
  0x1f12254d,0xaea7adc2,0xa311a94d,0x329431b6,0x2c792d2a,0xa4209d7f,0xb074b122,0x281f217f,0x2a312b91,0xa8d0a6e0,0xae2daf8b,0x2cce2ade,
  0x26e028d0,0xab91aa31,0xaadeacce,0x2f8b2e2d,0x1d7f2420,0xad2aac79,0xa17fa81f,0x31223074,0x2a632b5f,0xa1e49bdb,0xae5faf59,0x25e41fdb,
  0x286b2967,0xa6e0a4e9,0xac6aad65,0x2ade28e8,0x24e926e0,0xa967a86b,0xa8e8aade,0x2d652c6a,0x1bdb21e4,0xab5faa63,0x9fdba5e4,0x2f592e5f,
  0x27a9286b,0x9f1298b6,0xaba7ac6a,0x23111cb6,0x254d267b,0xa420a1e4,0xa94daa7a,0x281f25e4,0x21e42420,0xa67ba54d,0xa5e4a81f,0x2a7a294d,
  0x18b61f12,0xa86ba7a9,0x9cb6a311,0x2c6a2ba7,0x211b21e4,0x98b69248,0xa51ba5e4,0x1cb61648,0x1f122052,0x9d7f9bdb,0xa311a452,0x217f1fdb,
  0x1bdb1d7f,0xa0529f12,0x9fdba17f,0x24522311,0x124818b6,0xa1e4a11b,0x96489cb6,0x25e4251b,0xa11ba1e4,0x18b61248,0x251b25e4,0x9cb69648,
  0x9f12a052,0x1d7f1bdb,0x23112452,0xa17f9fdb,0x9bdb9d7f,0x20521f12,0x1fdb217f,0xa452a311,0x924898b6,0x21e4211b,0x16481cb6,0xa5e4a51b,
  0xa7a9a86b,0x1f1218b6,0x2ba72c6a,0xa3119cb6,0xa54da67b,0x242021e4,0x294d2a7a,0xa81fa5e4,0xa1e4a420,0x267b254d,0x25e4281f,0xaa7aa94d,
  0x98b69f12,0x286b27a9,0x1cb62311,0xac6aaba7,0xaa63ab5f,0x21e41bdb,0x2e5f2f59,0xa5e49fdb,0xa86ba967,0x26e024e9,0x2c6a2d65,0xaadea8e8,
  0xa4e9a6e0,0x2967286b,0x28e82ade,0xad65ac6a,0x9bdba1e4,0x2b5f2a63,0x1fdb25e4,0xaf59ae5f,0xac79ad2a,0x24201d7f,0x30743122,0xa81fa17f,
  0xaa31ab91,0x28d026e0,0x2e2d2f8b,0xacceaade,0xa6e0a8d0,0x2b912a31,0x2ade2cce,0xaf8bae2d,0x9d7fa420,0x2d2a2c79,0x217f281f,0xb122b074,
  0xadc2aea7,0x254d1f12,0x31b63294,0xa94da311,0xabf6acde,0x2a31286b,0x2fef30d7,0xae2dac6a,0xa86baa31,0x2cde2bf6,0x2c6a2e2d,0xb0d7afef,
  0x9f12a54d,0x2ea72dc2,0x2311294d,0xb294b1b6,0xaf0cb012,0x267b2052,0x32f73402,0xaa7aa452,0xacdeadf5,0x2b912967,0x30d731e8,0xaf8bad65,
  0xa967ab91,0x2df52cde,0x2d652f8b,0xb1e8b0d7,0xa052a67b,0x30122f0c,0x24522a7a,0xb402b2f7,0xb02cb0d2,0x27a9211b,0x341a34b7,0xaba7a51b,
  0xadc2af0c,0x2c792a63,0x31b632f7,0xb074ae5f,0xaa63ac79,0x2f0c2dc2,0x2e5f3074,0xb2f7b1b6,0xa11ba7a9,0x30d2302c,0x251b2ba7,0xb4b7b41a,
  0xb0d2b194,0x286b21e4,0x34b7356a,0xac6aa5e4,0xaea7b012,0x2d2a2b5f,0x32943402,0xb122af59,0xab5fad2a,0x30122ea7,0x2f593122,0xb402b294,
  0xa1e4a86b,0x319430d2,0x25e42c6a,0xb56ab4b7,0xb17ab257,0x290222ad,0x3552361a,0xad00a6ad,0xaf8cb09f,0x2ddc2c2e,0x33713487,0xb1cfb029,
  0xac2eaddc,0x309f2f8c,0x302931cf,0xb487b371,0xa2ada902,0x3257317a,0x26ad2d00,0xb61ab552,0xb223b31c,0x29992376,0x35eb36c6,0xad97a776,
  0xb039b12d,0x2e8d2cac,0x3426350b,0xb27cb0a6,0xacacae8d,0x312d3039,0x30a6327c,0xb50bb426,0xa376a999,0x331c3223,0x27762d97,0xb6c6b5eb,
  0xb2cdb3e3,0x2a312420,0x3682376f,0xae2da81f,0xb0acb1bb,0x2f3f2d2a,0x3493358d,0xb328b122,0xad2aaf3f,0x31bb30ac,0x31223328,0xb58db493,
  0xa420aa31,0x33e332cd,0x281f2e2d,0xb76fb682,0xb378b456,0x2ac82484,0x3715380a,0xaec3a884,0xb120b24a,0x2ff22da9,0x34ff360e,0xb3d3b19e,
  0xada9aff2,0x324a3120,0x319e33d3,0xb60eb4ff,0xa484aac8,0x34563378,0x28842ec3,0xb80ab715,0xb413b4bc,0x2b5f24e9,0x37a6385a,0xaf59a8e8,
  0xb194b2da,0x30522e28,0x356a368d,0xb43eb219,0xae28b052,0x32da3194,0x3219343e,0xb68db56a,0xa4e9ab5f,0x34bc3413,0x28e82f59,0xb85ab7a6,
  0xb46ab523,0x2bf6254d,0x381a38a8,0xafefa94d,0xb209b36b,0x30ac2ea7,0x35d4370a,0xb493b294,0xaea7b0ac,0x336b3209,0x32943493,0xb70ab5d4,
  0xa54dabf6,0x3523346a,0x294d2fef,0xb8a8b81a,0xb4c3b58c,0x2c4725b2,0x385f38f3,0xb042a9b1,0xb27eb3fd,0x31062f26,0x363c3785,0xb4e7b30f,
  0xaf26b106,0x33fd327e,0x330f34e7,0xb785b63c,0xa5b2ac47,0x358c34c3,0x29b13042,0xb8f3b85f,0xb51cb5f6,0x2c932617,0x38a3393c,0xb08daa16,
  0xb2f4b448,0x31602fa5,0x36a437fe,0xb53ab389,0xafa5b160,0x344832f4,0x3389353a,0xb7feb6a4,0xa617ac93,0x35f6351c,0x2a16308d,0xb93cb8a3,
};
__device__ __align__(128) const uint32_t c_img[2560] = {
  0x326d31ed,0x333b32dd,0x33c33388,0x33fe33ea,0x33c331ed,0x31ed33c3,0xa8b22d64,0xb33bb0c4,0x33ea31ed,0xad64301d,0xb2ddb388,0x315fa8b2,
  0x32dd31ed,0xb3feabc6,0x326dad64,0xad64326d,0x30c431ed,0xaed7b2dd,0x2bc63388,0xa248b3ea,0x2bc631ed,0x315fb3c3,0xb3ea2d64,0x2ed730c4,
  0xa8b231ed,0x3388b01d,0x301db388,0xb1ed28b2,0xb01d31ed,0x22482bc6,0x30c4ad64,0x3388b26d,0x33ea33fe,0x338833c3,0x32dd333b,0x31ed326d,
  0xb2ddb3fe,0xa248b01d,0x326d2ed7,0x338833ea,0x30c433fe,0xb33babc6,0xabc6b33b,0x33fe30c4,0xabc6b3fe,0x31ed32dd,0xb3eaaed7,0x333ba8b2,
  0xa8b233fe,0x2d64b3c3,0xb01d333b,0x315fb26d,0x301db3fe,0xb3fe301d,0x30c42ed7,0x2d64b3ea,0xb26d33fe,0x2ed72bc6,0x33c3b33b,0xa248b0c4,
  0x33c3b3fe,0x315fb2dd,0x28b2aed7,0xaed728b2,0xb0c4b15f,0xaed7b01d,0xabc6ad64,0xa248a8b2,0xabc6b15f,0x315f2bc6,0x33ea3388,0x2ed7326d,
  0x28b2b15f,0x338832dd,0xb01d2d64,0xb1edb3ea,0x301db15f,0x224833c3,0xb0c4b388,0x338830c4,0x326db15f,0xb33b301d,0x33c3ad64,0xb3fe28b2,
  0x33c3b15f,0xb1edabc6,0xa8b23388,0x333bb26d,0x33eab15f,0x2d64b2dd,0xb2dd2d64,0xb15f33ea,0x32ddb15f,0x33feb3c3,0x326db388,0x2d64b0c4,
  0x28b22248,0x2d642bc6,0x301d2ed7,0x315f30c4,0xb01da248,0xb3feb2dd,0xb0c4b33b,0x2d64a8b2,0x326d2248,0x2ed733c3,0xb3c3aed7,0xa248b26d,
  0xb3c3a248,0x315fb01d,0xa8b2333b,0xaed7b3ea,0x33ea2248,0xb388abc6,0x32dd2ed7,0xb1edb0c4,0xb2dda248,0x224832dd,0x326db33b,0xb38828b2,
  0x30c42248,0x333bb3c3,0xabc6aed7,0xb3fe326d,0xabc6a248,0xb1ed301d,0xb3ea333b,0xb33b33ea,0xb26d31ed,0xb33b32dd,0xb3c33388,0xb3fe33ea,
  0xb3c331ed,0xb1ed33c3,0x28b22d64,0x333bb0c4,0xb3ea31ed,0x2d64301d,0x32ddb388,0xb15fa8b2,0xb2dd31ed,0x33feabc6,0xb26dad64,0x2d64326d,
  0xb0c431ed,0x2ed7b2dd,0xabc63388,0x2248b3ea,0xabc631ed,0xb15fb3c3,0x33ea2d64,0xaed730c4,0x28b231ed,0xb388b01d,0xb01db388,0x31ed28b2,
  0x301d31ed,0xa2482bc6,0xb0c4ad64,0xb388b26d,0xb3ea33fe,0xb38833c3,0xb2dd333b,0xb1ed326d,0x32ddb3fe,0x2248b01d,0xb26d2ed7,0xb38833ea,
  0xb0c433fe,0x333babc6,0x2bc6b33b,0xb3fe30c4,0x2bc6b3fe,0xb1ed32dd,0x33eaaed7,0xb33ba8b2,0x28b233fe,0xad64b3c3,0x301d333b,0xb15fb26d,
  0xb01db3fe,0x33fe301d,0xb0c42ed7,0xad64b3ea,0x326d33fe,0xaed72bc6,0xb3c3b33b,0x2248b0c4,0xb3c3b3fe,0xb15fb2dd,0xa8b2aed7,0x2ed728b2,
  0x30c4b15f,0x2ed7b01d,0x2bc6ad64,0x2248a8b2,0x2bc6b15f,0xb15f2bc6,0xb3ea3388,0xaed7326d,0xa8b2b15f,0xb38832dd,0x301d2d64,0x31edb3ea,
  0xb01db15f,0xa24833c3,0x30c4b388,0xb38830c4,0xb26db15f,0x333b301d,0xb3c3ad64,0x33fe28b2,0xb3c3b15f,0x31edabc6,0x28b23388,0xb33bb26d,
  0xb3eab15f,0xad64b2dd,0x32dd2d64,0x315f33ea,0xb2ddb15f,0xb3feb3c3,0xb26db388,0xad64b0c4,0xa8b22248,0xad642bc6,0xb01d2ed7,0xb15f30c4,
  0x301da248,0x33feb2dd,0x30c4b33b,0xad64a8b2,0xb26d2248,0xaed733c3,0x33c3aed7,0x2248b26d,0x33c3a248,0xb15fb01d,0x28b2333b,0x2ed7b3ea,
  0xb3ea2248,0x3388abc6,0xb2dd2ed7,0x31edb0c4,0x32dda248,0xa24832dd,0xb26db33b,0x338828b2,0xb0c42248,0xb33bb3c3,0x2bc6aed7,0x33fe326d,
  0x2bc6a248,0x31ed301d,0x33ea333b,0x333b33ea,0x30c4315f,0x2ed7301d,0x2bc62d64,0x224828b2,0x2bc6315f,0xb15fabc6,0xb3eab388,0xaed7b26d,
  0xa8b2315f,0xb388b2dd,0x301dad64,0x31ed33ea,0xb01d315f,0xa248b3c3,0x30c43388,0xb388b0c4,0xb26d315f,0x333bb01d,0xb3c32d64,0x33fea8b2,
  0xb3c3315f,0x31ed2bc6,0x28b2b388,0xb33b326d,0xb3ea315f,0xad6432dd,0x32ddad64,0x315fb3ea,0xb2dd315f,0xb3fe33c3,0xb26d3388,0xad6430c4,
  0xa8b2a248,0xad64abc6,0xb01daed7,0xb15fb0c4,0x301d2248,0x33fe32dd,0x30c4333b,0xad6428b2,0xb26da248,0xaed7b3c3,0x33c32ed7,0x2248326d,
  0x33c32248,0xb15f301d,0x28b2b33b,0x2ed733ea,0xb3eaa248,0x33882bc6,0xb2ddaed7,0x31ed30c4,0x32dd2248,0xa248b2dd,0xb26d333b,0x3388a8b2,
  0xb0c4a248,0xb33b33c3,0x2bc62ed7,0x33feb26d,0x2bc62248,0x31edb01d,0x33eab33b,0x333bb3ea,0x326d31ed,0x333b32dd,0x33c33388,0x33fe33ea,
  0x33c331ed,0x31ed33c3,0xa8b22d64,0xb33bb0c4,0x33ea31ed,0xad64301d,0xb2ddb388,0x315fa8b2,0x32dd31ed,0xb3feabc6,0x326dad64,0xad64326d,
  0x30c431ed,0xaed7b2dd,0x2bc63388,0xa248b3ea,0x2bc631ed,0x315fb3c3,0xb3ea2d64,0x2ed730c4,0xa8b231ed,0x3388b01d,0x301db388,0xb1ed28b2,
  0xb01d31ed,0x22482bc6,0x30c4ad64,0x3388b26d,0x33ea33fe,0x338833c3,0x32dd333b,0x31ed326d,0xb2ddb3fe,0xa248b01d,0x326d2ed7,0x338833ea,
  0x30c433fe,0xb33babc6,0xabc6b33b,0x33fe30c4,0xabc6b3fe,0x31ed32dd,0xb3eaaed7,0x333ba8b2,0xa8b233fe,0x2d64b3c3,0xb01d333b,0x315fb26d,
  0x301db3fe,0xb3fe301d,0x30c42ed7,0x2d64b3ea,0xb26d33fe,0x2ed72bc6,0x33c3b33b,0xa248b0c4,0x33c3b3fe,0x315fb2dd,0x28b2aed7,0xaed728b2,
  0xb0c4315f,0xaed7301d,0xabc62d64,0xa24828b2,0xabc6315f,0x315fabc6,0x33eab388,0x2ed7b26d,0x28b2315f,0x3388b2dd,0xb01dad64,0xb1ed33ea,
  0x301d315f,0x2248b3c3,0xb0c43388,0x3388b0c4,0x326d315f,0xb33bb01d,0x33c32d64,0xb3fea8b2,0x33c3315f,0xb1ed2bc6,0xa8b2b388,0x333b326d,
  0x33ea315f,0x2d6432dd,0xb2ddad64,0xb15fb3ea,0x32dd315f,0x33fe33c3,0x326d3388,0x2d6430c4,0x28b2a248,0x2d64abc6,0x301daed7,0x315fb0c4,
  0xb01d2248,0xb3fe32dd,0xb0c4333b,0x2d6428b2,0x326da248,0x2ed7b3c3,0xb3c32ed7,0xa248326d,0xb3c32248,0x315f301d,0xa8b2b33b,0xaed733ea,
  0x33eaa248,0xb3882bc6,0x32ddaed7,0xb1ed30c4,0xb2dd2248,0x2248b2dd,0x326d333b,0xb388a8b2,0x30c4a248,0x333b33c3,0xabc62ed7,0xb3feb26d,
  0xabc62248,0xb1edb01d,0xb3eab33b,0xb33bb3ea,0xb26d31ed,0xb33b32dd,0xb3c33388,0xb3fe33ea,0xb3c331ed,0xb1ed33c3,0x28b22d64,0x333bb0c4,
  0xb3ea31ed,0x2d64301d,0x32ddb388,0xb15fa8b2,0xb2dd31ed,0x33feabc6,0xb26dad64,0x2d64326d,0xb0c431ed,0x2ed7b2dd,0xabc63388,0x2248b3ea,
  0xabc631ed,0xb15fb3c3,0x33ea2d64,0xaed730c4,0x28b231ed,0xb388b01d,0xb01db388,0x31ed28b2,0x301d31ed,0xa2482bc6,0xb0c4ad64,0xb388b26d,
  0xb3ea33fe,0xb38833c3,0xb2dd333b,0xb1ed326d,0x32ddb3fe,0x2248b01d,0xb26d2ed7,0xb38833ea,0xb0c433fe,0x333babc6,0x2bc6b33b,0xb3fe30c4,
  0x2bc6b3fe,0xb1ed32dd,0x33eaaed7,0xb33ba8b2,0x28b233fe,0xad64b3c3,0x301d333b,0xb15fb26d,0xb01db3fe,0x33fe301d,0xb0c42ed7,0xad64b3ea,
  0x326d33fe,0xaed72bc6,0xb3c3b33b,0x2248b0c4,0xb3c3b3fe,0xb15fb2dd,0xa8b2aed7,0x2ed728b2,0x29ed29ed,0x29ed29ed,0x29ed29ed,0x29ed29ed,
  0x2bc32a6d,0x2add2bea,0x23c628c4,0xa81da0b2,0x2bc32add,0xa3c6281d,0xabc3aadd,0x23c6a81d,0x29ed2b3b,0xabfea564,0x295fa6d7,0x1a482b88,
  0x25642b88,0xa564ab88,0x25642b88,0xa564ab88,0xa0b22bc3,0x2a6daadd,0xabea23c6,0x28c4281d,0xa8c42bea,0x2a6da0b2,0x28c4abea,0xaa6d20b2,
  0xab3b2bfe,0xa564295f,0x26d79a48,0x2b88a9ed,0x29ed29ed,0x29ed29ed,0x29ed29ed,0x29ed29ed,0xabc3aa6d,0xaaddabea,0xa3c6a8c4,0x281d20b2,
  0x2bc32add,0xa3c6281d,0xabc3aadd,0x23c6a81d,0xa9edab3b,0x2bfe2564,0xa95f26d7,0x9a48ab88,0x25642b88,0xa564ab88,0x25642b88,0xa564ab88,
  0x20b2abc3,0xaa6d2add,0x2beaa3c6,0xa8c4a81d,0xa8c42bea,0x2a6da0b2,0x28c4abea,0xaa6d20b2,0x2b3babfe,0x2564a95f,0xa6d71a48,0xab8829ed,
  0x295f295f,0x295f295f,0x295f295f,0x295f295f,0x23c628c4,0xa81da0b2,0xabc3aa6d,0xaaddabea,0xa3c6281d,0xabc3aadd,0x23c6a81d,0x2bc32add,
  0xa95f26d7,0x9a48ab88,0x29ed2b3b,0xabfea564,0xab882564,0x2b88a564,0xab882564,0x2b88a564,0xabea23c6,0x28c4281d,0x20b2abc3,0xaa6d2add,
  0xaa6d20b2,0xa8c42bea,0x2a6da0b2,0x28c4abea,0xa6d71a48,0xab8829ed,0xab3b2bfe,0xa564295f,0x295f295f,0x295f295f,0x295f295f,0x295f295f,
  0xa3c6a8c4,0x281d20b2,0x2bc32a6d,0x2add2bea,0xa3c6281d,0xabc3aadd,0x23c6a81d,0x2bc32add,0x295fa6d7,0x1a482b88,0xa9edab3b,0x2bfe2564,
  0xab882564,0x2b88a564,0xab882564,0x2b88a564,0x2beaa3c6,0xa8c4a81d,0xa0b22bc3,0x2a6daadd,0xaa6d20b2,0xa8c42bea,0x2a6da0b2,0x28c4abea,
  0x26d79a48,0x2b88a9ed,0x2b3babfe,0x2564a95f,0xabfe2bfe,0xabfe2bfe,0xabfe2bfe,0xabfe2bfe,0xaadd2bea,0xa3c628c4,0x281da0b2,0x2bc3aa6d,
  0xa81d2bc3,0x2adda3c6,0x281dabc3,0xaadd23c6,0x9a482b88,0x29edab3b,0xabfe2564,0x295f26d7,0x26d72b3b,0xa6d7ab3b,0x26d72b3b,0xa6d7ab3b,
  0x2a6d2add,0xabeaa3c6,0x28c4a81d,0x20b22bc3,0x2bea2a6d,0xa0b228c4,0xabeaaa6d,0x20b2a8c4,0x2b8829ed,0x2b3b2bfe,0x2564295f,0xa6d79a48,
  0xabfe2bfe,0xabfe2bfe,0xabfe2bfe,0xabfe2bfe,0x2addabea,0x23c6a8c4,0xa81d20b2,0xabc32a6d,0xa81d2bc3,0x2adda3c6,0x281dabc3,0xaadd23c6,
  0x1a48ab88,0xa9ed2b3b,0x2bfea564,0xa95fa6d7,0x26d72b3b,0xa6d7ab3b,0x26d72b3b,0xa6d7ab3b,0xaa6daadd,0x2bea23c6,0xa8c4281d,0xa0b2abc3,
  0x2bea2a6d,0xa0b228c4,0xabeaaa6d,0x20b2a8c4,0xab88a9ed,0xab3babfe,0xa564a95f,0x26d71a48,0x1a489a48,0x1a489a48,0x1a489a48,0x1a489a48,
  0x281da0b2,0x2bc3aa6d,0x2addabea,0x23c6a8c4,0x2adda3c6,0x281dabc3,0xaadd23c6,0xa81d2bc3,0x2bfea564,0xa95fa6d7,0x9a482b88,0x29edab3b,
  0x2b3ba6d7,0xab3b26d7,0x2b3ba6d7,0xab3b26d7,0x28c4a81d,0x20b22bc3,0xaa6daadd,0x2bea23c6,0x20b2a8c4,0x2bea2a6d,0xa0b228c4,0xabeaaa6d,
  0xa564a95f,0x26d71a48,0x2b8829ed,0x2b3b2bfe,0x1a489a48,0x1a489a48,0x1a489a48,0x1a489a48,0xa81d20b2,0xabc32a6d,0xaadd2bea,0xa3c628c4,
  0x2adda3c6,0x281dabc3,0xaadd23c6,0xa81d2bc3,0xabfe2564,0x295f26d7,0x1a48ab88,0xa9ed2b3b,0x2b3ba6d7,0xab3b26d7,0x2b3ba6d7,0xab3b26d7,
  0xa8c4281d,0xa0b2abc3,0x2a6d2add,0xabeaa3c6,0x20b2a8c4,0x2bea2a6d,0xa0b228c4,0xabeaaa6d,0x2564295f,0xa6d79a48,0xab88a9ed,0xab3babfe,
  0xa95fa95f,0xa95fa95f,0xa95fa95f,0xa95fa95f,0xa3c6a8c4,0x281d20b2,0x2bc32a6d,0x2add2bea,0x23c6a81d,0x2bc32add,0xa3c6281d,0xabc3aadd,
  0x295fa6d7,0x1a482b88,0xa9edab3b,0x2bfe2564,0x2b88a564,0xab882564,0x2b88a564,0xab882564,0x2beaa3c6,0xa8c4a81d,0xa0b22bc3,0x2a6daadd,
  0x2a6da0b2,0x28c4abea,0xaa6d20b2,0xa8c42bea,0x26d79a48,0x2b88a9ed,0x2b3babfe,0x2564a95f,0xa95fa95f,0xa95fa95f,0xa95fa95f,0xa95fa95f,
  0x23c628c4,0xa81da0b2,0xabc3aa6d,0xaaddabea,0x23c6a81d,0x2bc32add,0xa3c6281d,0xabc3aadd,0xa95f26d7,0x9a48ab88,0x29ed2b3b,0xabfea564,
  0x2b88a564,0xab882564,0x2b88a564,0xab882564,0xabea23c6,0x28c4281d,0x20b2abc3,0xaa6d2add,0x2a6da0b2,0x28c4abea,0xaa6d20b2,0xa8c42bea,
  0xa6d71a48,0xab8829ed,0xab3b2bfe,0xa564295f,0x29ed29ed,0x29ed29ed,0x29ed29ed,0x29ed29ed,0x2bc32a6d,0x2add2bea,0x23c628c4,0xa81da0b2,
  0x2bc32add,0xa3c6281d,0xabc3aadd,0x23c6a81d,0x29ed2b3b,0xabfea564,0x295fa6d7,0x1a482b88,0x25642b88,0xa564ab88,0x25642b88,0xa564ab88,
  0xa0b22bc3,0x2a6daadd,0xabea23c6,0x28c4281d,0xa8c42bea,0x2a6da0b2,0x28c4abea,0xaa6d20b2,0xab3b2bfe,0xa564295f,0x26d79a48,0x2b88a9ed,
  0x29ed29ed,0x29ed29ed,0x29ed29ed,0x29ed29ed,0xabc3aa6d,0xaaddabea,0xa3c6a8c4,0x281d20b2,0x2bc32add,0xa3c6281d,0xabc3aadd,0x23c6a81d,
  0xa9edab3b,0x2bfe2564,0xa95f26d7,0x9a48ab88,0x25642b88,0xa564ab88,0x25642b88,0xa564ab88,0x20b2abc3,0xaa6d2add,0x2beaa3c6,0xa8c4a81d,
  0xa8c42bea,0x2a6da0b2,0x28c4abea,0xaa6d20b2,0x2b3babfe,0x2564a95f,0xa6d71a48,0xab8829ed,0x9a481a48,0x9a481a48,0x9a481a48,0x9a481a48,
  0xa81d20b2,0xabc32a6d,0xaadd2bea,0xa3c628c4,0xaadd23c6,0xa81d2bc3,0x2adda3c6,0x281dabc3,0xabfe2564,0x295f26d7,0x1a48ab88,0xa9ed2b3b,
  0xab3b26d7,0x2b3ba6d7,0xab3b26d7,0x2b3ba6d7,0xa8c4281d,0xa0b2abc3,0x2a6d2add,0xabeaa3c6,0xa0b228c4,0xabeaaa6d,0x20b2a8c4,0x2bea2a6d,
  0x2564295f,0xa6d79a48,0xab88a9ed,0xab3babfe,0x9a481a48,0x9a481a48,0x9a481a48,0x9a481a48,0x281da0b2,0x2bc3aa6d,0x2addabea,0x23c6a8c4,
  0xaadd23c6,0xa81d2bc3,0x2adda3c6,0x281dabc3,0x2bfea564,0xa95fa6d7,0x9a482b88,0x29edab3b,0xab3b26d7,0x2b3ba6d7,0xab3b26d7,0x2b3ba6d7,
  0x28c4a81d,0x20b22bc3,0xaa6daadd,0x2bea23c6,0xa0b228c4,0xabeaaa6d,0x20b2a8c4,0x2bea2a6d,0xa564a95f,0x26d71a48,0x2b8829ed,0x2b3b2bfe,
  0xabfe2bfe,0xabfe2bfe,0xabfe2bfe,0xabfe2bfe,0xaadd2bea,0xa3c628c4,0x281da0b2,0x2bc3aa6d,0xa81d2bc3,0x2adda3c6,0x281dabc3,0xaadd23c6,
  0x9a482b88,0x29edab3b,0xabfe2564,0x295f26d7,0x26d72b3b,0xa6d7ab3b,0x26d72b3b,0xa6d7ab3b,0x2a6d2add,0xabeaa3c6,0x28c4a81d,0x20b22bc3,
  0x2bea2a6d,0xa0b228c4,0xabeaaa6d,0x20b2a8c4,0x2b8829ed,0x2b3b2bfe,0x2564295f,0xa6d79a48,0xabfe2bfe,0xabfe2bfe,0xabfe2bfe,0xabfe2bfe,
  0x2addabea,0x23c6a8c4,0xa81d20b2,0xabc32a6d,0xa81d2bc3,0x2adda3c6,0x281dabc3,0xaadd23c6,0x1a48ab88,0xa9ed2b3b,0x2bfea564,0xa95fa6d7,
  0x26d72b3b,0xa6d7ab3b,0x26d72b3b,0xa6d7ab3b,0xaa6daadd,0x2bea23c6,0xa8c4281d,0xa0b2abc3,0x2bea2a6d,0xa0b228c4,0xabeaaa6d,0x20b2a8c4,
  0xab88a9ed,0xab3babfe,0xa564a95f,0x26d71a48,0x3bfb3bff,0x3be53bf2,0x3bbf3bd4,0x3b873ba5,0x3bd03bfb,0x3b013b7c,0x399d3a60,0x378538bc,
  0x35173b52,0xbbc9b7c8,0xb074ba9b,0x3bfe391b,0x319e3b27,0xbbf3b979,0x363cb80a,0x3a2d3bc5,0xba093986,0x3a7eb8f8,0xbae5385f,0x3b3db77a,
  0xbabd393c,0x3bb0b699,0xbc00305b,0x3ba730d7,0xbb2a35c8,0xb8353bb2,0x3a64b1e8,0x3962bbf7,0xba90350b,0xba413bff,0x3602340e,0x3bf6bad8,
  0xac6aa5e4,0xb122af59,0xb402b294,0xb56ab4b7,0xb2deac9c,0xb7bdb5a5,0xb9b3b8d6,0xbb10ba73,0xbb96b676,0xb359bafe,0x3bec3884,0x2a163a29,
  0xbbe0b72c,0x2f27b9d6,0x3b5e3ae8,0xb91633a2,0xb941b9c9,0x38ad3a45,0xb80fbab3,0x36d23b13,0xb850ba0d,0x346f3b4a,0x1fdbbbed,0xb4ab3be8,
  0x3721bb76,0xbace3463,0xb8d13bdd,0x39ebadfb,0x3894bb98,0xb8fd281f,0xbb6a3bbd,0x2e2d3825,0x3b3f3b65,0x3ae83b16,0x3a813ab6,0x3a0d3a49,
  0x3263356a,0xad972b43,0xb5dfb359,0xb8eeb7f3,0xa9b139aa,0xbbedba25,0x3340b889,0x3b983afb,0xbaa2aa16,0xb4cfbb8e,0x3c0038ad,0xb44b38e5,
  0xbb853625,0x3bbdb4c3,0xbbe432ad,0x3bfbaf8b,0xbaacb6d2,0x39243954,0xb65fbace,0x2fbd3bb8,0xb9661648,0xba603bf8,0x383a31cf,0x3b27bbb3,
  0x3219b9eb,0xbb1836f4,0xb9903be5,0x37dd3010,0xb6c6b61a,0xb80ab76f,0xb8a8b85a,0xb93cb8f3,0xbbd7bb87,0xbbf8bbfd,0xbb71bbc9,0xba4dbaf1,
  0xbbfeb9a6,0x305bb91f,0x3bcb3a97,0xb50b37d2,0xb87abbfe,0x3ba13546,0x24523a7e,0xbbb5ba54,0xb576bb63,0x340e3ba3,0xb13bbbd3,0x2c9c3bf2,
  0x386abb3d,0xba2139f8,0x3b57b835,0xbbf13432,0x39e7bc00,0xb8d6adc9,0xbacb3bde,0x372c3457,0x3bdab962,0x3764bb35,0xb9c03122,0xbaf73bef,
  0x398b39cd,0x38fd3946,0x386538b2,0x37853815,0xba85b9c9,0xbb92bb1e,0xbbfebbdd,0xbbc2bbf5,0xb66b3682,0xbb01bb94,0x387fb371,0x3a2d3beb,
  0xbac7bb76,0x3a00ad33,0x36bb3bd4,0xbbeab79b,0xbc0026ad,0x3bf32c38,0xbbd6b109,0x3ba733eb,0x3153bbff,0xb70a3b9e,0x396bba9b,0xbade390c,
  0xb5d4b5bc,0xbbb03b2c,0x32013830,0x3bf6ba67,0x3bccbb52,0x2c06b92e,0xbb83385f,0xb8c73bab,0xb9c5b982,0xba41ba04,0xbab0ba7a,0xbb10bae1,
  0xb8a3b986,0xb52fb74e,0xa94db1e8,0x33d32e91,0xbb54bb4f,0x37bdb523,0x3a9e3bc8,0xb916308d,0x3840b5c8,0x394a3bf9,0xbb42b294,0xb0a6bb0a,
  0x251bbbff,0xaf273bfc,0x327cbbe6,0xb4ab3bc0,0x3be325e4,0xbb2fb4e7,0x39e33884,0xb81aba35,0x3b73bb78,0xb46fb715,0xbbdc3ad1,0x2e2d38cc,
  0x33283676,0x3bfcba19,0x3581bab3,0xba6b3493,0x363136dd,0x34cf3581,0x32c6341a,0x2fbd3153,0xbae1bb65,0xb970ba39,0xb715b889,0xb16cb4f3,
  0xb9a12a7a,0xb924bbfe,0x3a933042,0x37dd3bcc,0x308db9aa,0x3b453b07,0xb94632ad,0xb845bbfa,0xbb68b55e,0x3b1836bb,0xbabab805,0x3a4d38a3,
  0x3bc0b625,0xbbfe2ec3,0x3b9431cf,0xba89b742,0x9cb6b95d,0xbbf8396b,0xb1b63a5c,0x3bb5b840,0x38cc9648,0x3b81bbac,0xac38b85a,0xbbce3933,
  0xbb60bb3a,0xbba1bb83,0xbbd2bbbc,0xbbf1bbe3,0x3815361a,0x39df3907,0x3b2c3a97,0x3be23b9c,0xb9afbbfd,0x3a21294d,0x388e3bee,0xbaf7b328,
  0x3beb39a6,0xb6af37a6,0xba04bbd3,0x3ac42d00,0x360ebb89,0xb7643b42,0x3855baeb,0xb8ee3a85,0x33eb3b63,0x28e8bbf5,0xb5233bde,0x389ebb21,
  0x3c00b9f0,0x2d97b9e3,0xbbdf38db,0xb44b3ac7,0xba673c00,0x358d3487,0x3bfcbab6,0x330fba15,0x3b7a3bf1,0x394a3a93,0x33893764,0xb3d39cb6,
  0x3afb3be2,0x35eb3946,0xb4c328e8,0xbaa9b8cc,0x27763af7,0xbb2fbaba,0x3a76ad97,0x30a63b60,0xaf8b3ac4,0xb994bb94,0x3bf8358d,0xb8743815,
  0xbb4c38ee,0x3bfcb1b6,0xbad5b4cf,0x381a39af,0xbbb3389e,0x3b592c38,0xb76fb970,0xb24b3beb,0xb9d2344b,0xbb923bd2,0xb0f03924,0x3a6bb60e,
  0xb8f3330f,0xbc003b2c,0xb91f3b45,0x323233eb,0xb5b1afbd,0xba00b88e,0xbbc6bb18,0xbbc2bc00,0xb7d2b16c,0xbb6fba04,0xbba3bbfe,0xb86fba67,
  0xbbffb7dd,0x370ab855,0x38b73bf8,0xbbeab631,0xbbf2b845,0x39bcb523,0x2dc93b81,0xbaa5bae1,0xb68dba4d,0xac063bdf,0x382abba1,0xbade39a1,
  0xb457ba89,0xb6543bfc,0x3b16b9df,0xbbd8308d,0x397dbbb5,0xb52fb2c6,0xbbe73a21,0xb8c73b68,0x3a49bbce,0x2311b715,0xba2536af,0xbbd93bc0,
  0xb958b785,0xbb81ba9e,0xbbefbbf3,0xba89bb73,0xbbf7bbc2,0xb9b8bb42,0xaf59b70a,0x384a3328,0xbb8bba2d,0x39dfb27c,0x34263bb0,0xbbceb98b,
  0xb4b7bbea,0x3b6c39e3,0xbafe2c06,0x3185ba85,0xaadebba7,0xb6af3bdc,0x3a58ba41,0xbbe2366b,0x3a29bade,0xbc003581,0x3a45352f,0xb2f7bac7,
  0x3b37bbf6,0x28e8b865,0xbaee37bd,0xbac43c00,0x3b13b8c7,0x3b5cbbfe,0x3463b94a,0xb8993153,0xb9f4bb10,0xb58db87f,0x3029af27,0x389e35d4,
  0x2dfbb3d3,0x399936bb,0x3bf23b2f,0x3ac13bcc,0x3552b916,0x39703bd6,0xbbbab46f,0x330fb9c5,0x3ba530a6,0xb5f7396b,0xb7c8bbfc,0x3be138a3,
  0x3bfdb4ab,0xbb45b201,0x38e038fd,0xb16cbb54,0x391b381a,0xa17fbb83,0xb8f83b92,0x3bcfb840,0x36e82e2d,0x3bfebab0,0x37febb01,0xb845251b,
  0xb77a3a6b,0x3648294d,0x3bb2ba00,0x3a8cbbe3,0xb742b93c,0x2311b340,0x37a6340e,0x3aa93966,0x3b963a4d,0x3b7f3c00,0x380f3a21,0xb0be3219,
  0x3933b50b,0x35eb3be4,0xbbf5b8d6,0x3874b6c6,0x39413bb5,0xbbffb65f,0x38d1b764,0x33ba3bd7,0x3b9c2c9c,0xb994b83a,0x34873ae8,0x324bbbfe,
  0xb7213bf1,0x3b47b990,0xbbbf2d97,0x38c1387a,0x2d00372c,0x3b59b8a8,0x3a39bbed,0xb232b576,0xbbfb3af7,0xb9743b71,0x307434cf,0x3adbb86a,
  0x3b213a0d,0x3c003bcb,0x3b073bbd,0x386f39e7,0x351738ee,0xb599a452,0xbae5b924,0xbbe9bbda,0x3a153b98,0xbb6fb13b,0x2ec3ba60,0x3aa53b3f,
  0xba09344b,0xa884bb57,0x3a643b18,0xbbc3b263,0xb4f33bfb,0x39bcbacb,0xbbac380a,0x3bd8a9b1,0xbb2aafbd,0x36a439c0,0x3402bbf8,0xba6f3aa2,
  0xbbfa3b27,0xb6543a81,0x3907b05b,0x3bd9bb85,0x2c6ab7dd,0xb9da35df,0xbbec3ba1,0xb8203aac,0x3bf53b87,0x3b6c3bec,0x392e3a7e,0x32f73721,
  0xb9e7b785,0xbbfcbb5e,0xba81bbb0,0xb43eb894,0x379b3bfe,0xbc00b80f,0x374eb835,0x38993bfb,0xbb3fba2d,0x3b329fdb,0xb3403a41,0xb8eabbd0,
  0xb90c3b3d,0x3b5cb8d1,0xbbf93122,0x3ac13517,0x29b1bba7,0xb94f3b6a,0x3be4b7bd,0xbaf4b19e,0xbbab3962,0xb9993bbf,0x34e73359,0x3be1ba09,
  0x3b85bbf6,0x353ab99d,0xb83a2f27,0xbbf03abd,0x2e91356a,0xb5f7b074,0xba19b8ad,0xbbcfbb2a,0xb966bb10,0xaba7b63c,0x38a8346f,0x3bb73a90,
  0xbb0aaa16,0xa17fbae5,0x3b1e3ace,0xba8c2c6a,0x36c6b916,0x36ff3c00,0xbbcbb8fd,0x3a50b2de,0xba35b6d2,0x36483a64,0x2d33bbe5,0xb84a3b96,
  0x3bfeb4ab,0xb9fcb602,0x313b3b01,0x37e8bbe0,0x3493b9eb,0xb9b83402,0xbb9e3bc9,0xb1853941,0x35762e2d,0x3b90b9b3,0x3acbbbf3,0x2fefb850,
  0x3a543bcf,0x2884374e,0xb9f8b648,0xbbe9bbab,0x398b3bb7,0xb4db3340,0xbbdcb9fc,0xb911bb85,0xb4323a8c,0xb6a4bbf9,0x3b3539b8,0xbbc3ae91,
  0xb66b3a50,0xad65bbe4,0x38653b90,0xbb0db966,0xbbef384a,0x39da34e7,0x2b43bb6c,0xba6f3b0a,0xbc0037e8,0x3759383a,0x387fbbfc,0xbbf636c6,
  0xb7f33185,0xbb7f3a19,0xbb8e3c00,0xb8203a35,0xb5d42fef,0xba1d38a8,0xbbd63b32,0xbba93bfe,0xb8e5b2f7,0xbbffbb1e,0xb954bb5c,0x30beb493,
  0xb9c5b43e,0xbb9fbbcb,0xb201b94f,0x3a313576,0xbbb8b899,0x3b47ad33,0xb6f43999,0xb3babbf5,0xbb54b8ea,0x3bf9313b,0xbab0353a,0x3790b9e7,
  0xb010bac1,0xb9743b9e,0x3bfdb5f7,0xb8c1b79b,0x251bbaf4,0xbb1b3acb,0x3a9e2ba7,0x2e5fbb3f,0x3af1bbe1,0x3599b92e,0xb546a17f,0xbadb390c,
  0x3b73bbf0,0x3929ba81,0x327cb6ff,0xb49f29b1,0xb825baa9,0x353aaec3,0x3b7c3994,0x3af43bfa,0x360eb0be,0x3bf43a64,0x388e3b47,0xb7372c6a,
  0x38bcb874,0x2ba73bac,0xb979bb59,0x3bf03742,0x3c0033ba,0xbb043402,0x3855b974,0xacce3b96,0x3bc5b24b,0xb6ffb907,0xb6993c00,0x3bb7b933,
  0x363138c1,0x3902bbec,0xbbdf3599,0x34ff3941,0x30d73232,0x39fcb7a6,0x3bffbb6f,0x3a50bb9c,0xb9a13adb,0xb47b380f,0x32c62884,0x3937b721,
  0x3ad8386f,0x3b903bf5,0x35a539bc,0xb7e8ad00,0x3b683be9,0x2ef538d1,0xba93b6a4,0xbb24bbfb,0x3a733aa5,0xbbfcb487,0x39d6b654,0xafef3b21,
  0x1cb63bc3,0xb7b2bbbf,0x3aba39da,0xbbfab517,0xb3a23bd8,0x3b32ba39,0xbb4a2311,0x343e3a15,0xbb603a6f,0x3a3d3074,0x31b6bb7f,0xbb9a3a09,
  0xbbe83bd9,0xb94f3b07,0xa81f35eb,0x38eab4f3,0xb9af3820,0xbbae3ae5,0xbbd23bff,0xba113b2a,0x319e389e,0xb929b426,0xbc00bb45,0xb911bb37,
  0xbbffbac1,0xb805bafe,0x382a217f,0x3bfd3b13,0xbabd330f,0x34dbba58,0x36023bfe,0xbb0db9f4,0xb68dbbe1,0x3a5c3a45,0xbbe7b648,0x3b89adfb,
  0xba90b16c,0x2d653aee,0x39b3bb81,0xbbf63552,0x397dbbcf,0xbbbc3463,0x338939b8,0x39f0bba5,0x32deb845,0xb7593029,0xbb5e39df,0xbba93bfd,
  0x3b7aba8c,0x3beebbf2,0x3a76bb6c,0x36ddb91b,0xbbe0ba89,0xba1dbbba,0x1fdbb6af,0x3a3136e8,0xa776b84a,0x3aeb37c8,0x3ad53c00,0xaa7a377a,
  0xb850bbce,0x3b9f38e0,0xbb6a28e8,0x3790b958,0x3b4cb185,0xb8db38f8,0x30f0bb5c,0x355e3bf7,0x3894bbe2,0xbbf937fe,0x399d358d,0x2e5fbb8b,
  0x39d232f7,0x341abbb2,0xbbc63999,0x395d34b7,0x3bd0bac4,0x3b1bbbef,0x363cb970,0xb49faade,0xb5b13899,0x30422f59,0x38b7b5f7,0x3b3aba29,
  0x3219b3d3,0x3b0438b7,0x3b713bfc,0x34ff397d,0x36e83aa9,0xb8b2adc9,0xbbefbb59,0xb5bcba49,0x3bd730a6,0xb902382a,0xa452bb92,0x39373b7a,
  0xb9583874,0x3371bb16,0x34263c00,0xb982bafb,0x387a381a,0x347bbbe7,0xbb573a00,0x3b242776,0xbb8b324b,0x31093a25,0x3a58bb6f,0xbb4f2f8b,
  0xb86a3a6b,0x2ef53389,0x39c0b70a,0x3bfabb4c,0xaadeb232,0xb83034c3,0xbaee39bc,0xbbff3bb3,0x3bda3bc2,0x37b23a76,0xb5df2c06,0xbb9ab9d2,
  0xbb37b86f,0xba7abbf8,0x3029b654,0x3b7838f3,0x32633bea,0xba3dbad5,0x3c00352f,0xba1135b1,0xb9f4baa5,0x3bc8376f,0xbbba2311,0x39cdb7d2,
  0xbaa23ade,0x3baeb0f0,0xb65fb94a,0xb7373bff,0x3552bbd8,0xbbe6391f,0x38e035eb,0x3682bbf2,0xbaac38c7,0xbbf43bc6,0xb9903b2f,0xacce368d,
  0x3bfdbbd9,0x3ad1bba3,0x37feb994,0x26adb457,0x38a33b9a,0xb8dba452,0xbb83bbae,0x2a7ab86a,0x37423b78,0xbab6b426,0xb907bbe6,0x39aa2ade,
  0xb8403a11,0x341abb57,0x294d3bf4,0xb55ebbda,0xb93339cd,0x3889ba58,0xb7a63ad1,0x3625bb37,0xbbe33737,0x304239c0,0x3b42bb04,0xb95db263,
  0xbb9c3682,0xb2ad3aee,0x3bf5b8b2,0x1648b9f4,0xb3282cce,0xb80535df,0xb9e33902,0xbb3a3aa2,0xad0026ad,0xb1cf3029,0xb4873371,0xb61a3552,
  0xba85b4ff,0xba5cbc00,0x3581b47b,0x3bfd3aac,0xbb21b5bc,0xb85abbba,0x3a393109,0x39a63bfd,0xbac7b937,0x3bbc365f,0xbbfeaef5,0x3b89b219,
  0xba15b982,0x3a9738e0,0xbb07b830,0x3b6336e8,0x3153bb24,0xbbee3990,0x36bb37b2,0x39f0bbd7,0x34f3bb4f,0xbbd337fe,0xaec33a7a,0x3c00b958,
  0x3bccbbfa,0x3aebbb71,0x396bba3d,0x36ddb87a,0x3bfabbff,0x3bdebbef,0x3bacbbc8,0x3b65bb8b,0x3bc03911,0x38303b6a,0xb946ad65,0xbb4fbbd0,
  0x3a353bfd,0xb85f30f0,0xbb1ebbbc,0x35c8b5b1,0x38cc3b0d,0xba7ab99d,0x3b943759,0xbbffb19e,0xb4933b89,0x31e8bbc6,0xad333bee,0xa5e4bbff,
  0xb8153bf6,0x3bc8b63c,0xac38ba1d,0xbb783abd,0xbbf539f0,0x329438b7,0x3b9ebaeb,0xb676b68d,0xbbeb3ba9,0xbbe63c00,0xbb2c3b9f,0xb9cd3a90,
  0xb79b36dd,0xb884382a,0xb92e38db,0xb9c9397d,0x33eb3a31,0xbad1b602,0xba04bbf9,0x3682b2de,0xb90c2a7a,0xbab3bbe7,0x374eb41a,0x3b763b7a,
  0xba673790,0x38b2b9b3,0xb5233b1b,0x26adbbe0,0xbbabb55e,0x3bdd3389,0xbbf9b042,0x3bff2776,0xbae12e5f,0xb3713b5e,0x3bfcb929,0xb5bcb850,
  0xae91b95d,0xbbd43a76,0x34e73805,0x3b52bb4c,0x308db49f,0xb1091fdb,0xb71534db,0xb9823894,0x3b0abb3a,0x3a9bbad5,0x3a19ba5c,0x3986b9d2,
  0x2f8bb7e8,0x3bde3979,0x376f3b32,0xb9aab0d7,0x3bb83b24,0xb1223855,0xbbfdba3d,0xaa16b9a1,0x3bb3afef,0xbab63699,0x391fb94f,0xb6253ad8,
  0x30103bfa,0xb359bbdf,0x35463bae,0xb6d2bb68,0x38f3343e,0x3889bbff,0xbba3353a,0x96483a73,0xbaf13b9a,0x38ad32c6,0x39f8bbf4,0xb9eb9cb6,
  0xb7d238ea,0xb2ad35a5,0x2dc92ba7,0x361ab3a2,0xba543a11,0xbace3a93,0xbb353b04,0xbb873b60,0x3bf23af4,0x31cf39d6,0xbb16b6ff,0xb9a6bbe8,
  0xb4323737,0xbbe5baba,0x2b43b902,0x3bfe39af,0x34573bf0,0xb85abb4a,0x3a2539fc,0xbb63b825,0xbbef2cce,0x3bc9b1b6,0xbb8e347b,0x3b3db60e,
  0xba493bb7,0x3a97a81f,0x34c3bb90,0xbc0038bc,0xb7f3b4ff,0xba7e3bd2,0x39542ef5,0x3962bc00,0xbafb3a50,0xbbd33b7c,0xbbf83bfc,0xbb653bc5,
  0x38e5b937,0x3835b88e,0x36f4b7b2,0x356ab631,0xbb13bbe9,0x31e8b6f4,0x3bf239da,0x36763af1,0x3be83911,0x340e3ab0,0xbb7cb759,0xb72cbb73,
  0x2dfbbbc3,0x32943bfd,0xb7c8bb7f,0x39c93a54,0x38253b0d,0xb8d6ba9e,0x39793a1d,0xba0db98b,0x3ba5ba6f,0xb884b546,0xb8f83bff,0x3b76b432,
  0xb8bc3bf6,0x3ae8b27c,0x3699bb9f,0xbb98366b,0x391bb820,0x3ab3b9f8,0x3bb2bb47,0x3bffbbef,0xbbc53ba9,0xbbed3bdc,0xbbff3bf9,0xbbfb3c00,
  0x377ab0be,0x3bdd3b35,0x2f593974,0xbb52b7f3,0x30d73a31,0xbbbdb865,0xb5a5bb1b,0x3b2735d4,0x3bf733ba,0xbbd42b43,0x3afeb599,0xb98638e5,
  0xbad83790,0x3a60b87f,0xb9d63929,0x393cb9c5,0x34b738c1,0x3a9bbb8e,0xba45a884,0xb5c83bb8,0xba732e5f,0xb80a3bd6,0x3b4ab4db,0x350bbb54,
  0xba293adb,0xb85f3954,0xb46336a4,0x25e43010,0x33a2b49f,0x305bb201,0x281fad65,0xac9c251b,0x3f803f80,0x3f803f80,0x3f803f80,0x3f803f80,
  0x3f803f80,0x3f803f80,0x3f803f80,0x3f803f80,0x3f803f80,0x3f803f80,0x3f803f80,0x3f803f80,0x3f803f80,0x3f803f80,0x3f803f80,0x3f803f80,
  0x3f803f80,0x3f803f80,0x3f803f80,0x3f803f80,0x3f803f80,0x3f803f80,0x3f803f80,0x3f803f80,0x3f803f80,0x3f803f80,0x3f803f80,0x3f803f80,
  0x3f803f80,0x3f803f80,0x3f803f80,0x3f803f80,0x3f803f80,0x3f803f80,0x3f803f80,0x3f803f80,0x3f803f80,0x3f803f80,0x3f803f80,0x3f803f80,
  0x3f803f80,0x3f803f80,0x3f803f80,0x3f803f80,0x3f803f80,0x3f803f80,0x3f803f80,0x3f803f80,0x3f803f80,0x3f803f80,0x3f803f80,0x3f803f80,
  0x3f803f80,0x3f803f80,0x3f803f80,0x3f803f80,0x3f803f80,0x3f803f80,0x3f803f80,0x3f803f80,0x3f803f80,0x3f803f80,0x3f803f80,0x3f803f80,
  0x3f803f80,0x3f803f80,0x3f803f80,0x3f803f80,0x3f803f80,0x3f803f80,0x3f803f80,0x3f803f80,0x3f803f80,0x3f803f80,0x3f803f80,0x3f803f80,
  0x3f803f80,0x3f803f80,0x3f803f80,0x3f803f80,0x3f803f80,0x3f803f80,0x3f803f80,0x3f803f80,0x3f803f80,0x3f803f80,0x3f803f80,0x3f803f80,
  0x3f803f80,0x3f803f80,0x3f803f80,0x3f803f80,0x3f803f80,0x3f803f80,0x3f803f80,0x3f803f80,0x3f803f80,0x3f803f80,0x3f803f80,0x3f803f80,
  0x3f803f80,0x3f803f80,0x3f803f80,0x3f803f80,0x3f803f80,0x3f803f80,0x3f803f80,0x3f803f80,0x3f803f80,0x3f803f80,0x3f803f80,0x3f803f80,
  0x3f803f80,0x3f803f80,0x3f803f80,0x3f803f80,0x3f803f80,0x3f803f80,0x3f803f80,0x3f803f80,0x3f803f80,0x3f803f80,0x3f803f80,0x3f803f80,
  0x3f803f80,0x3f803f80,0x3f803f80,0x3f803f80,0x3f803f80,0x3f803f80,0x3f803f80,0x3f803f80,0x3f803f80,0x3f803f80,0x3f803f80,0x3f803f80,
  0x3f803f80,0x3f803f80,0x3f803f80,0x3f803f80,0x3f803f80,0x3f803f80,0x3f803f80,0x3f803f80,0x3f803f80,0x3f803f80,0x3f803f80,0x3f803f80,
  0x3f803f80,0x3f803f80,0x3f803f80,0x3f803f80,0x3f803f80,0x3f803f80,0x3f803f80,0x3f803f80,0x3f803f80,0x3f803f80,0x3f803f80,0x3f803f80,
  0x3f803f80,0x3f803f80,0x3f803f80,0x3f803f80,0x3f803f80,0x3f803f80,0x3f803f80,0x3f803f80,0x3f803f80,0x3f803f80,0x3f803f80,0x3f803f80,
  0x3f803f80,0x3f803f80,0x3f803f80,0x3f803f80,0x3f803f80,0x3f803f80,0x3f803f80,0x3f803f80,0x3f803f80,0x3f803f80,0x3f803f80,0x3f803f80,
  0x3f803f80,0x3f803f80,0x3f803f80,0x3f803f80,0x3f803f80,0x3f803f80,0x3f803f80,0x3f803f80,0x3f803f80,0x3f803f80,0x3f803f80,0x3f803f80,
  0x3f803f80,0x3f803f80,0x3f803f80,0x3f803f80,0x3f803f80,0x3f803f80,0x3f803f80,0x3f803f80,0x3f803f80,0x3f803f80,0x3f803f80,0x3f803f80,
  0x3f803f80,0x3f803f80,0x3f803f80,0x3f803f80,0x3f803f80,0x3f803f80,0x3f803f80,0x3f803f80,0x3f803f80,0x3f803f80,0x3f803f80,0x3f803f80,
  0x3f803f80,0x3f803f80,0x3f803f80,0x3f803f80,0x3f803f80,0x3f803f80,0x3f803f80,0x3f803f80,0x3f803f80,0x3f803f80,0x3f803f80,0x3f803f80,
  0x3f803f80,0x3f803f80,0x3f803f80,0x3f803f80,0x3f803f80,0x3f803f80,0x3f803f80,0x3f803f80,0x3f803f80,0x3f803f80,0x3f803f80,0x3f803f80,
  0x3f803f80,0x3f803f80,0x3f803f80,0x3f803f80,0x3f803f80,0x3f803f80,0x3f803f80,0x3f803f80,0x3f803f80,0x3f803f80,0x3f803f80,0x3f803f80,
  0x3f803f80,0x3f803f80,0x3f803f80,0x3f803f80,0x3f803f80,0x3f803f80,0x3f803f80,0x3f803f80,0x3f803f80,0x3f803f80,0x3f803f80,0x3f803f80,
  0x3f803f80,0x3f803f80,0x3f803f80,0x3f803f80,0x3f803f80,0x3f803f80,0x3f803f80,0x3f803f80,0x3f803f80,0x3f803f80,0x3f803f80,0x3f803f80,
  0x3f803f80,0x3f803f80,0x3f803f80,0x3f803f80,0x3f803f80,0x3f803f80,0x3f803f80,0x3f803f80,0x3f803f80,0x3f803f80,0x3f803f80,0x3f803f80,
  0x3f803f80,0x3f803f80,0x3f803f80,0x3f803f80,0x3f803f80,0x3f803f80,0x3f803f80,0x3f803f80,0x3f803f80,0x3f803f80,0x3f803f80,0x3f803f80,
  0x3f803f80,0x3f803f80,0x3f803f80,0x3f803f80,0x3f803f80,0x3f803f80,0x3f803f80,0x3f803f80,0x3f803f80,0x3f803f80,0x3f803f80,0x3f803f80,
  0x3f803f80,0x3f803f80,0x3f803f80,0x3f803f80,0x3f803f80,0x3f803f80,0x3f803f80,0x3f803f80,0x3f803f80,0x3f803f80,0x3f803f80,0x3f803f80,
  0x3f803f80,0x3f803f80,0x3f803f80,0x3f803f80,0x3f803f80,0x3f803f80,0x3f803f80,0x3f803f80,0x3f803f80,0x3f803f80,0x3f803f80,0x3f803f80,
  0x3f803f80,0x3f803f80,0x3f803f80,0x3f803f80,0x3f803f80,0x3f803f80,0x3f803f80,0x3f803f80,0x3f803f80,0x3f803f80,0x3f803f80,0x3f803f80,
  0x3f803f80,0x3f803f80,0x3f803f80,0x3f803f80,0x3f803f80,0x3f803f80,0x3f803f80,0x3f803f80,0x3f803f80,0x3f803f80,0x3f803f80,0x3f803f80,
  0x3f803f80,0x3f803f80,0x3f803f80,0x3f803f80,0x3f803f80,0x3f803f80,0x3f803f80,0x3f803f80,0x3f803f80,0x3f803f80,0x3f803f80,0x3f803f80,
  0x3f803f80,0x3f803f80,0x3f803f80,0x3f803f80,0x3f803f80,0x3f803f80,0x3f803f80,0x3f803f80,0x3f803f80,0x3f803f80,0x3f803f80,0x3f803f80,
  0x3f803f80,0x3f803f80,0x3f803f80,0x3f803f80,0x3f803f80,0x3f803f80,0x3f803f80,0x3f803f80,0x3f803f80,0x3f803f80,0x3f803f80,0x3f803f80,
  0x3f803f80,0x3f803f80,0x3f803f80,0x3f803f80,0x3f803f80,0x3f803f80,0x3f803f80,0x3f803f80,0x3f803f80,0x3f803f80,0x3f803f80,0x3f803f80,
  0x3f803f80,0x3f803f80,0x3f803f80,0x3f803f80,0x3f803f80,0x3f803f80,0x3f803f80,0x3f803f80,0x3f803f80,0x3f803f80,0x3f803f80,0x3f803f80,
  0x3f803f80,0x3f803f80,0x3f803f80,0x3f803f80,0x3f803f80,0x3f803f80,0x3f803f80,0x3f803f80,0x3f803f80,0x3f803f80,0x3f803f80,0x3f803f80,
  0x3f803f80,0x3f803f80,0x3f803f80,0x3f803f80,0x3f803f80,0x3f803f80,0x3f803f80,0x3f803f80,0x3f803f80,0x3f803f80,0x3f803f80,0x3f803f80,
  0x3f803f80,0x3f803f80,0x3f803f80,0x3f803f80,0x3f803f80,0x3f803f80,0x3f803f80,0x3f803f80,0x3f803f80,0x3f803f80,0x3f803f80,0x3f803f80,
  0x3f803f80,0x3f803f80,0x3f803f80,0x3f803f80,0x3f803f80,0x3f803f80,0x3f803f80,0x3f803f80,0x3f803f80,0x3f803f80,0x3f803f80,0x3f803f80,
  0x3f803f80,0x3f803f80,0x3f803f80,0x3f803f80,0x3f803f80,0x3f803f80,0x3f803f80,0x3f803f80,0x3f803f80,0x3f803f80,0x3f803f80,0x3f803f80,
  0x3f803f80,0x3f803f80,0x3f803f80,0x3f803f80,0x3f803f80,0x3f803f80,0x3f803f80,0x3f803f80,0x3f803f80,0x3f803f80,0x3f803f80,0x3f803f80,
  0x3f803f80,0x3f803f80,0x3f803f80,0x3f803f80,0x3f803f80,0x3f803f80,0x3f803f80,0x3f803f80,0x3f803f80,0x3f803f80,0x3f803f80,0x3f803f80,
  0x3f803f80,0x3f803f80,0x3f803f80,0x3f803f80,
};

__device__ __align__(128) float    g_part[16][8][2176];
__device__ __align__(128) float    g_kv[16][2176];
__device__ __align__(128) uint4    g_o[16 * 16 * 1024];
__device__ __align__(128) unsigned g_ocnt[2 * 16 * 32];
__device__ unsigned g_epoch[128];
#define GSTAMP(role, i) do {} while (0)
#define STAMP(role, i) do {} while (0)
#define PDUMP(role) do {} while (0)
#define PROF_SMEM 0

constexpr int STAGE_BYTES = 57344;
constexpr int OFF_H = 4 * 16384, OFF_VP = 9 * 16384, OFF_SPARE = 10 * 16384;
constexpr int OFF_XT = 172032, XT_STRIDE = 4112;
constexpr int OFF_BAR = 204928, OFF_EPOCH = OFF_BAR + 640, OFF_EX = OFF_BAR + 656, OFF_D = OFF_BAR + 672, OFF_SCALE = OFF_BAR + 704;
constexpr int OFF_F2F = 205824, OFF_F2I = 207872, OFF_F4 = 209920, OFF_ONES = 214016, OFF_KVB = 214016;
constexpr int OFF_STG = 219136, STG_STRIDE = 4352, SMEM_TOTAL = 232192 + PROF_SMEM;
enum { B_FULL1 = 0, B_EMPTY1 = 3, B_Q = 6, B_ODONE1 = 7, B_O1RDY = 8, B_H = 9, B_XRAW = 10, B_XT = 11, B_KV = 12, B_Y = 13,  B_AFREE = 15,
       B_STG = 18, B_ODONE = 24, B_XFREE = 25, B_FULL2 = 33, B_CONS2 = 49, B_SFREE = 14, B_PKRDY = 62, B_PKFREE = 64, B_H2 = 65, B_COUNT = 66 };
__host__ __device__ constexpr int bar_count(int i) {
  return i < B_EMPTY1 ? 1 : i < B_Q ? 4 : i == B_XT ? 4 : i == B_H ? 4 : i == B_SFREE ? 2 : i >= B_PKFREE ? 4 : i >= B_PKRDY ? 8 : i == B_KV ? 2 : i == B_Y ? 9
       : (i >= B_AFREE && i < B_STG) ? 16 : (i == B_ODONE || i == B_ODONE1) ? 8 : (i >= B_XFREE && i < B_FULL2) ? 4
       : (i >= B_CONS2 && i <= B_CONS2 + 10) ? 4 : i >= B_CONS2 ? 2 : (i >= B_FULL2 && i < B_FULL2 + 7) ? 2 : 1;
}
__host__ __device__ constexpr uint64_t bar_counts(int r) {
  uint64_t v = 0;
  for (int w = 0; w < 11; w++) v |= (uint64_t)(bar_count(1 + 11 * r + w) - 1) << (4 * w);
  return v;
}
constexpr uint64_t SLOT_A = 0x9645296452964594ull;
constexpr uint64_t SLOT_B = 0x7310873108731026ull;
constexpr uint32_t SW128 = 64 | (1u << 30);
constexpr int SPIN_LIMIT = 1 << 22;
#define PKV CU_TENSOR_MAP_L2_PROMOTION_L2_128B
#define BPRE B_KV
#define PFD 3
#define PD1 0
#define PD2 100
#define E1C 2
#define OSP 4
#define QPF 6
#define TSPLIT 1
#define OC0 2
#define OC1 2
#define BSPL 4
#define BPACE 250
#define NPOS 0
#define O1POS 1
#define HL1 4
#define OCH 3
#define O1D 3
#define QPOS 2
#define HOLD2 13
#define A0COL 0
#define KPOS 1
#define CWAIT 0
#define HSTART 1500
#define PACE 800
#define OC 1

__device__ __forceinline__ uint32_t smem_u32(const void* p) { return (uint32_t)__cvta_generic_to_shared(p); }
__device__ __forceinline__ void wg_fence() { asm volatile("wgmma.fence.sync.aligned;" ::: "memory"); }
__device__ __forceinline__ void wg_commit() { asm volatile("wgmma.commit_group.sync.aligned;" ::: "memory"); }
template <int N> __device__ __forceinline__ void wg_wait() { asm volatile("wgmma.wait_group.sync.aligned %0;" ::"n"(N) : "memory"); }
template <int N> __device__ __forceinline__ void keep(float (&d)[N]) {
#pragma unroll
  for (int i = 0; i < N; i++) asm volatile("" : "+f"(d[i])::"memory");
}
__device__ __forceinline__ uint64_t mkdesc(uint32_t addr, uint32_t lbo, uint32_t sbo, uint32_t swz) {
  uint32_t lo = ((addr & 0x3FFFF) >> 4) | ((lbo >> 4) << 16), hi = (sbo >> 4) | (swz << 30);
  return ((uint64_t)hi << 32) | lo;
}
__device__ __forceinline__ void mbar_init(uint32_t bar, int cnt) { asm volatile("mbarrier.init.shared::cta.b64 [%0], %1;" ::"r"(bar), "r"(cnt)); }
__device__ __forceinline__ void mbar_expect(uint32_t bar, int bytes) { asm volatile("mbarrier.arrive.expect_tx.shared::cta.b64 _, [%0], %1;" ::"r"(bar), "r"(bytes) : "memory"); }
__device__ __forceinline__ void mbar_arrive(uint32_t bar) { asm volatile("mbarrier.arrive.shared::cta.b64 _, [%0];" ::"r"(bar) : "memory"); }
__device__ __forceinline__ void mbar_arrive_cl(uint32_t bar, uint32_t cta) {
  asm volatile("{\n.reg .b32 r;\nmapa.shared::cluster.u32 r, %0, %1;\nmbarrier.arrive.shared::cluster.b64 _, [r];\n}\n" ::"r"(bar), "r"(cta) : "memory");
}
__device__ __forceinline__ void mbar_wait(uint32_t bar, uint32_t parity) {
  asm volatile("{\n.reg .pred p;\n.reg .u32 n;\nmov.u32 n, 0;\n"
               "W_%=:\nmbarrier.try_wait.parity.shared::cta.b64 p, [%0], %1;\n@p bra D_%=;\n"
               "add.u32 n, n, 1;\nsetp.lt.u32 p, n, %2;\n@p bra W_%=;\ntrap;\nD_%=:\n}\n" ::"r"(bar), "r"(parity), "n"(SPIN_LIMIT) : "memory");
}
__device__ __forceinline__ void fence_async() { asm volatile("fence.proxy.async.shared::cta;" ::: "memory"); }
__device__ __forceinline__ void bar_sync(int id) { asm volatile("bar.sync %0, 128;" ::"r"(id) : "memory"); }
__device__ __forceinline__ void tma2d(uint32_t dst, const CUtensorMap* m, int c0, int c1, uint32_t bar) {
  asm volatile("cp.async.bulk.tensor.2d.shared::cluster.global.mbarrier::complete_tx::bytes [%0], [%1, {%3, %4}], [%2];"
               ::"r"(dst), "l"(m), "r"(bar), "r"(c0), "r"(c1) : "memory");
}
__device__ __forceinline__ void tma2d_mc(uint32_t dst, const CUtensorMap* m, int c0, int c1, uint32_t bar) {
  asm volatile("cp.async.bulk.tensor.2d.shared::cluster.global.mbarrier::complete_tx::bytes.multicast::cluster [%0], [%1, {%3, %4}], [%2], %5;"
               ::"r"(dst), "l"(m), "r"(bar), "r"(c0), "r"(c1), "h"((uint16_t)3) : "memory");
}
__device__ __forceinline__ void tma3d(uint32_t dst, const CUtensorMap* m, int c0, int c1, int c2, uint32_t bar) {
  asm volatile("cp.async.bulk.tensor.3d.shared::cluster.global.mbarrier::complete_tx::bytes [%0], [%1, {%3, %4, %5}], [%2];"
               ::"r"(dst), "l"(m), "r"(bar), "r"(c0), "r"(c1), "r"(c2) : "memory");
}
__device__ __forceinline__ void tma4d(uint32_t dst, const CUtensorMap* m, int c0, int c1, int c2, int c3, uint32_t bar) {
  asm volatile("cp.async.bulk.tensor.4d.shared::cluster.global.mbarrier::complete_tx::bytes [%0], [%1, {%3, %4, %5, %6}], [%2];"
               ::"r"(dst), "l"(m), "r"(bar), "r"(c0), "r"(c1), "r"(c2), "r"(c3) : "memory");
}
__device__ __forceinline__ void bulk_ld(uint32_t dst, const void* src, int bytes, uint32_t bar) {
  asm volatile("cp.async.bulk.shared::cluster.global.mbarrier::complete_tx::bytes [%0], [%1], %2, [%3];" ::"r"(dst), "l"(src), "r"(bytes), "r"(bar) : "memory");
}
__device__ __forceinline__ void bulk_ld_mc(uint32_t dst, const void* src, int bytes, uint32_t bar) {
  asm volatile("cp.async.bulk.shared::cluster.global.mbarrier::complete_tx::bytes.multicast::cluster [%0], [%1], %2, [%3], %4;"
               ::"r"(dst), "l"(src), "r"(bytes), "r"(bar), "h"((uint16_t)3) : "memory");
}
__device__ __forceinline__ void tma2d_st(const CUtensorMap* m, uint32_t src, int c0, int c1) {
  asm volatile("cp.async.bulk.tensor.2d.global.shared::cta.bulk_group [%0, {%2, %3}], [%1];" ::"l"(m), "r"(src), "r"(c0), "r"(c1) : "memory");
}
__device__ __forceinline__ void pf_l2(const void* p, int bytes) { asm volatile("cp.async.bulk.prefetch.L2.global [%0], %1;" ::"l"(p), "r"(bytes) : "memory"); }
__device__ __forceinline__ void pf_t2d(const CUtensorMap* m, int c0, int c1) {
  asm volatile("cp.async.bulk.prefetch.tensor.2d.L2.global [%0, {%1, %2}];" ::"l"(m), "r"(c0), "r"(c1) : "memory");
}
__device__ __forceinline__ void pf_t3d(const CUtensorMap* m, int c0, int c1, int c2) {
  asm volatile("cp.async.bulk.prefetch.tensor.3d.L2.global [%0, {%1, %2, %3}];" ::"l"(m), "r"(c0), "r"(c1), "r"(c2) : "memory");
}
__device__ __forceinline__ void ldsm4(uint32_t (&r)[4], uint32_t a) {
  asm volatile("ldmatrix.sync.aligned.m8n8.x4.shared.b16 {%0,%1,%2,%3}, [%4];" : "=r"(r[0]), "=r"(r[1]), "=r"(r[2]), "=r"(r[3]) : "r"(a) : "memory");
}
__device__ __forceinline__ void ldsm4t(uint32_t (&r)[4], uint32_t a) {
  asm volatile("ldmatrix.sync.aligned.m8n8.x4.trans.shared.b16 {%0,%1,%2,%3}, [%4];" : "=r"(r[0]), "=r"(r[1]), "=r"(r[2]), "=r"(r[3]) : "r"(a) : "memory");
}
__device__ __forceinline__ void stsm4(uint32_t a, uint32_t r0, uint32_t r1, uint32_t r2, uint32_t r3) {
  asm volatile("stmatrix.sync.aligned.m8n8.x4.shared.b16 [%0], {%1,%2,%3,%4};" ::"r"(a), "r"(r0), "r"(r1), "r"(r2), "r"(r3) : "memory");
}
__device__ __forceinline__ uint32_t pk2(float lo, float hi) { uint32_t r; asm("cvt.rn.bf16x2.f32 %0, %1, %2;" : "=r"(r) : "f"(hi), "f"(lo)); return r; }
__device__ __forceinline__ uint32_t hmul(uint32_t a, uint32_t b) { uint32_t r; asm("mul.rn.bf16x2 %0, %1, %2;" : "=r"(r) : "r"(a), "r"(b)); return r; }
__device__ __forceinline__ uint32_t hadd(uint32_t a, uint32_t b) { uint32_t r; asm("add.rn.bf16x2 %0, %1, %2;" : "=r"(r) : "r"(a), "r"(b)); return r; }
__device__ __forceinline__ uint32_t hmax(uint32_t a, uint32_t b) { uint32_t r; asm("max.bf16x2 %0, %1, %2;" : "=r"(r) : "r"(a), "r"(b)); return r; }
__device__ __forceinline__ uint32_t hmin(uint32_t a, uint32_t b) { uint32_t r; asm("min.bf16x2 %0, %1, %2;" : "=r"(r) : "r"(a), "r"(b)); return r; }
__device__ __forceinline__ uint32_t hmaxabs(uint32_t a, uint32_t b) { uint32_t r; asm("max.xorsign.abs.bf16x2 %0, %1, %2;" : "=r"(r) : "r"(a), "r"(b)); return r; }
__device__ __forceinline__ float ex2(float x) { float r; asm("ex2.approx.ftz.f32 %0, %1;" : "=f"(r) : "f"(x)); return r; }
__device__ __forceinline__ float rcp_fast(float x) { float r; asm("rcp.approx.ftz.f32 %0, %1;" : "=f"(r) : "f"(x)); return r; }
__device__ __forceinline__ uint32_t phi2(float lo, float hi) {
  uint32_t t;
  asm("cvt.rn.relu.bf16x2.f32 %0, %1, %2;" : "=r"(t) : "f"(hi), "f"(lo));
  const uint32_t e = pk2(ex2(lo * 1.4426950408889634f), ex2(hi * 1.4426950408889634f));
  return hadd(hadd(t, hmin(e, 0x3F803F80u)), 0x35863586u);
}
__device__ __forceinline__ bool opaque_true() { uint32_t v; asm volatile("mov.u32 %0, %%nctaid.y;" : "=r"(v)); return v != 0; }
__device__ __forceinline__ int normalise(uint32_t (&v)[32], float fd) {
  const float f0 = fd + __uint_as_float(v[0] << 16);
  uint32_t m[4] = {hmaxabs(__float_as_uint(f0) >> 16, v[0]), v[1], v[2], v[3]};
#pragma unroll
  for (int i = 4; i < 32; i++) m[i & 3] = hmaxabs(m[i & 3], v[i]);
  m[0] = hmaxabs(hmaxabs(m[0], m[1]), hmaxabs(m[2], m[3]));
  const int e = min(max((int)(__reduce_max_sync(~0u, max(m[0] & 0x7FFFu, (m[0] >> 16) & 0x7FFFu)) >> 7), 1), 253);
  if (e > 141) {
#pragma unroll
    for (int i = 0; i < 32; i++) v[i] = hmul(v[i], 0x07000700u);
  }
  const uint32_t sc = (e > 141 ? 255 - e : 142 - e) * 0x00800080u;
#pragma unroll
  for (int i = 0; i < 32; i++) {
    const uint32_t a = hmul(v[i], sc);
    v[i] = (a & 0x0FFF0FFFu) * 7 + a;
  }
  v[0] = __byte_perm(v[0], __half_as_ushort(__float2half_rn(f0 * __uint_as_float((254 - e) << 23))), 0x3254);
  return e;
}
__device__ __forceinline__ void poll_ge(const unsigned* p, unsigned target) {
#pragma unroll 1
  for (int n = 0; n < SPIN_LIMIT; n++) {
    unsigned v;
    asm volatile("ld.relaxed.gpu.global.u32 %0, [%1];" : "=r"(v) : "l"(p) : "memory");
    if (__all_sync(~0u, (int)(v - target) >= 0)) { asm volatile("fence.acquire.gpu;" ::: "memory"); return; }
  }
  __trap();
}

__device__ __forceinline__ bool elect_one() {
  uint32_t p;
  asm volatile("{\n.reg .pred p;\nelect.sync _|p, 0xffffffff;\nselp.u32 %0, 1, 0, p;\n}\n" : "=r"(p));
  return p;
}
__device__ __forceinline__ uint4 ld_nc4(const void* p) {
  uint4 v;
  asm volatile("ld.global.nc.L1::no_allocate.v4.u32 {%0,%1,%2,%3}, [%4];" : "=r"(v.x), "=r"(v.y), "=r"(v.z), "=r"(v.w) : "l"(p));
  return v;
}
__device__ __forceinline__ void st_cg4(void* p, uint4 v) {
  asm volatile("st.global.cg.v4.u32 [%0], {%1,%2,%3,%4};" ::"l"(p), "r"(v.x), "r"(v.y), "r"(v.z), "r"(v.w) : "memory");
}
__device__ __forceinline__ uint32_t mapa(uint32_t a, uint32_t cta) { uint32_t r; asm("mapa.shared::cluster.u32 %0, %1, %2;" : "=r"(r) : "r"(a), "r"(cta)); return r; }
__device__ __forceinline__ void st_async(uint32_t a, uint32_t v, uint32_t bar) {
  asm volatile("st.async.weak.shared::cluster.mbarrier::complete_tx::bytes.b32 [%0], %1, [%2];" ::"r"(a), "r"(v), "r"(bar) : "memory");
}
__device__ __forceinline__ void st_async4(uint32_t a, uint32_t x, uint32_t y, uint32_t z, uint32_t w, uint32_t bar) {
  asm volatile("st.async.weak.shared::cluster.mbarrier::complete_tx::bytes.v4.b32 [%0], {%1,%2,%3,%4}, [%5];" ::"r"(a), "r"(x), "r"(y), "r"(z), "r"(w), "r"(bar) : "memory");
}
__device__ __forceinline__ void tma3d_st(const CUtensorMap* m, uint32_t src, int c0, int c1, int c2) {
  asm volatile("cp.async.bulk.tensor.3d.global.shared::cta.bulk_group [%0, {%2, %3, %4}], [%1];" ::"l"(m), "r"(src), "r"(c0), "r"(c1), "r"(c2) : "memory");
}
__device__ __forceinline__ uint4 ld_rlx4(const void* p) {
  uint4 v;
  asm volatile("{\n.reg .b128 t;\n.reg .b64 a, b;\nld.relaxed.gpu.global.b128 t, [%4];\nmov.b128 {a, b}, t;\nmov.b64 {%0, %1}, a;\nmov.b64 {%2, %3}, b;\n}\n"
               : "=r"(v.x), "=r"(v.y), "=r"(v.z), "=r"(v.w) : "l"(p) : "memory");
  return v;
}
__device__ __forceinline__ void ld_stale4(uint4& v, const void* p, uint32_t tag) {
  asm volatile("{\n.reg .b128 t;\n.reg .b64 a, b;\n.reg .b32 x;\n.reg .pred p;\n"
               "lop3.b32 x, %0, %5, 1, 0x28;\nsetp.ne.u32 p, x, 0;\n"
               "mov.b64 a, {%0, %1};\nmov.b64 b, {%2, %3};\nmov.b128 t, {a, b};\n"
               "@p ld.relaxed.gpu.global.b128 t, [%4];\n"
               "mov.b128 {a, b}, t;\nmov.b64 {%0, %1}, a;\nmov.b64 {%2, %3}, b;\n}\n"
               : "+r"(v.x), "+r"(v.y), "+r"(v.z), "+r"(v.w) : "l"(p), "r"(tag) : "memory");
}
__device__ __forceinline__ void st_tag4(void* p, float a, float b, float c, float d, uint32_t tag) {
  asm volatile("{\n.reg .b128 t;\n.reg .b64 a, b;\nmov.b64 a, {%1, %2};\nmov.b64 b, {%3, %4};\nmov.b128 t, {a, b};\nst.relaxed.gpu.global.b128 [%0], t;\n}\n"
               ::"l"(p), "r"((__float_as_uint(a) & ~1u) | tag), "f"(b), "f"(c), "f"(d) : "memory");
}
__device__ __forceinline__ uint32_t stale8(const uint4 (&f)[8], uint32_t tag) {
  uint32_t r[4];
#pragma unroll
  for (int i = 0; i < 4; i++) asm("lop3.b32 %0, %1, %2, %3, 0x7E;" : "=r"(r[i]) : "r"(f[2 * i].x), "r"(f[2 * i + 1].x), "r"(tag));
  asm("lop3.b32 %0, %0, %1, %2, 0xFE;" : "+r"(r[0]) : "r"(r[1]), "r"(r[2]));
  return r[0] | r[3];
}

struct ConvC { uint32_t a1[2][4], wa[2], wb[2], sg; };
__device__ __forceinline__ uint64_t dsc(uint32_t lo, uint32_t hi) { return ((uint64_t)hi << 32) | lo; }
__device__ __forceinline__ uint32_t hfma(uint32_t a, uint32_t b, uint32_t c) { uint32_t r; asm("fma.rn.f16x2 %0, %1, %2, %3;" : "=r"(r) : "r"(a), "r"(b), "r"(c)); return r; }
__device__ __forceinline__ uint32_t hfnma(uint32_t a, uint32_t b, uint32_t c) { uint32_t r; asm("{.reg .b32 n; neg.f16x2 n, %1; fma.rn.f16x2 %0, n, %2, %3;}" : "=r"(r) : "r"(a), "r"(b), "r"(c)); return r; }
__device__ __forceinline__ uint32_t hmul16(uint32_t a, uint32_t b) { uint32_t r; asm("mul.rn.f16x2 %0, %1, %2;" : "=r"(r) : "r"(a), "r"(b)); return r; }
template <int N> __device__ __forceinline__ void keepu(uint32_t (&d)[N]) {
#pragma unroll
  for (int i = 0; i < N; i++) asm volatile("" : "+r"(d[i])::"memory");
}
__device__ __forceinline__ void conv_m1(const ConvC& K, uint32_t (&u)[16], uint32_t l) {
  wg_fence();
  wgmma_hrs_n64<1>(u, K.a1[0][0], K.a1[0][1], K.a1[0][2], K.a1[0][3], dsc(l, 32), 0);
  wgmma_hrs_n64<1>(u, K.a1[1][0], K.a1[1][1], K.a1[1][2], K.a1[1][3], dsc(l + 16, 32), 1);
  wg_commit();
}
__device__ __forceinline__ void conv_s2(const ConvC& K, uint32_t (&u)[16], uint32_t (&Z)[2][8], uint32_t dfl) {
  uint32_t fr[8], fi[8];
#pragma unroll
  for (int c = 0; c < 8; c++) {
    const uint32_t r = hfma(K.wa[c & 1], u[2 * c + 1], u[2 * c]);
    fi[c] = hfma(K.wb[c & 1], r, u[2 * c + 1]);
    fr[c] = hfma(K.wa[c & 1], fi[c], r);
  }
  wg_fence();
#pragma unroll
  for (int p = 0; p < 2; p++) {
    wgmma_hrs_n32<0>(Z[p], fr[4 * p], fr[4 * p + 2], fr[4 * p + 1], fr[4 * p + 3], dsc(dfl, 32), 0);
    wgmma_hrs_n32<0>(Z[p], fi[4 * p], fi[4 * p + 2], fi[4 * p + 1], fi[4 * p + 3], dsc(dfl + 16, 32), 1);
  }
  wg_commit();
}
__device__ __forceinline__ void conv_win(const ConvC& K, const uint32_t (&X)[2][8], uint32_t (&W)[2][8]) {
#pragma unroll
  for (int b = 0; b < 4; b++)
#pragma unroll
    for (int c = 0; c < 2; c++) {
      const uint32_t xr = X[b >> 1][2 * c + (b & 1)], xi = X[b >> 1][4 + 2 * c + (b & 1)];
      const int a = b ? b - 1 : 0;
      W[b >> 1][2 * c + (b & 1)] = b ? hfnma(K.sg, X[a >> 1][4 + 2 * c + (a & 1)], xr) : hmul16(xr, 0x3C003C00u);
      W[b >> 1][4 + 2 * c + (b & 1)] = b ? hfma(K.sg, X[a >> 1][2 * c + (a & 1)], xi) : hmul16(xi, 0x3C003C00u);
    }
}
template <int p>
__device__ __forceinline__ void conv_pw(uint32_t (&X)[2][8], uint32_t (&H)[2][8], uint32_t (&V)[8], uint32_t dil) {
  uint32_t pr[2][2], pi[2][2];
#pragma unroll
  for (int jj = 0; jj < 2; jj++)
#pragma unroll
    for (int c = 0; c < 2; c++) {
      const int j = 2 * p + jj;
      uint32_t sr = 0, si = 0;
#pragma unroll
      for (int a = 0; a <= j; a++) {
        const int b = j - a;
        const uint32_t hr = H[a >> 1][2 * c + (a & 1)], hi = H[a >> 1][4 + 2 * c + (a & 1)];
        const uint32_t xr = X[b >> 1][2 * c + (b & 1)], xi = X[b >> 1][4 + 2 * c + (b & 1)];
        sr = a == 0 ? hmul16(hr, xr) : hfma(hr, xr, sr);
        si = a == 0 ? hmul16(hr, xi) : hfma(hr, xi, si);
        sr = hfnma(hi, xi, sr);
        si = hfma(hi, xr, si);
      }
      pr[jj][c] = sr; pi[jj][c] = si;
    }
  wg_fence();
  wgmma_hrs_n32<0>(V, pr[0][0], pr[1][0], pr[0][1], pr[1][1], dsc(dil, 32), 0);
  wgmma_hrs_n32<0>(V, pi[0][0], pi[1][0], pi[0][1], pi[1][1], dsc(dil + 16, 32), 1);
  wg_commit();
}
template <int p>
__device__ __forceinline__ void conv_it(const ConvC& K, uint32_t (&V)[8], uint32_t vst) {
#pragma unroll
  for (int jj = 0; jj < 2; jj++) {
    uint32_t wr[2], wi[2];
#pragma unroll
    for (int c = 0; c < 2; c++) {
      const uint32_t r = hfnma(K.wa[c], V[4 + 2 * c + jj], V[2 * c + jj]);
      wi[c] = hfnma(K.wb[c], r, V[4 + 2 * c + jj]);
      wr[c] = hfnma(K.wa[c], wi[c], r);
    }
    stsm4(vst + (2 * p + jj) * 2048, wr[0], wr[1], wi[0], wi[1]);
  }
}
__device__ __forceinline__ void conv_m4(uint32_t (&y)[8], uint32_t (&a)[4][4], uint32_t d4l) {
  wg_fence();
  wgmma_hrs_n32<0>(y, a[0][0], a[0][1], a[0][2], a[0][3], dsc(d4l, 64), 0);
#pragma unroll
  for (int s = 1; s < 4; s++) wgmma_hrs_n32<0>(y, a[s][0], a[s][1], a[s][2], a[s][3], dsc(d4l + s * 16, 64), 1);
  wg_commit();
}

struct Params {
  CUtensorMap tmX, tmW, tmWo, tmWo1, tmK, tmV, tmQ, tmOA, tmOB;
  const __nv_bfloat16 *shift_k, *h, *D, *x, *w, *wo, *q;
  float *part, *kv;
  uint4* o;
  unsigned *ocnt, *epoch;
  const uint32_t *thr, *img;
};

__global__ void __cluster_dims__(2, 1, 1) __launch_bounds__(384, 1) fused_kernel(const __grid_constant__ Params P) {
  extern __shared__ __align__(1024) uint8_t smem[];
  const uint32_t sb = smem_u32(smem);
  const uint32_t bars = sb + OFF_BAR;
  const int tid = threadIdx.x, lane = tid & 31;
  const int warp = __shfl_sync(~0u, tid >> 5, 0);
  const int rank = blockIdx.x & 1, cl = blockIdx.x >> 1;
  const int mb = cl < 4 ? 4 + cl : cl < 36 ? (cl - 4) >> 3 : 4 + (cl - 36) / 7;
  const int hb = (cl - 36) % 7;
  const int hq = cl < 4 ? A0COL : cl < 36 ? (cl - 4) & 7 : hb + (hb >= A0COL);
  const int hp = 2 * hq + rank;
  const int rb = 2 * mb + (hq >> 2), cb = hq & 3;
#define BAR(i) (bars + 8 * (i))

  if (tid == 0) { STAMP(0, 0); GSTAMP(0, 30); }
  if (warp == 8) {
    if (elect_one()) {
      mbar_init(BAR(B_FULL1), 1);
      asm volatile("fence.mbarrier_init.release.cluster;" ::: "memory");
      mbar_expect(BAR(B_FULL1), STAGE_BYTES);
      tma3d(sb + 32768, &P.tmW, hp * 64, 0, 0, BAR(B_FULL1));
    }
    if (lane == 0) STAMP(3, 21);
  } else if (lane == 0) {
    const int wi = warp - (warp > 8);
#pragma unroll
    for (int r = 0; r < 6; r++)
      if (r < 5 || wi < B_COUNT - 56) mbar_init(BAR(1 + 11 * r + wi), ((uint32_t)(bar_counts(r) >> (4 * wi)) & 15) + 1);
    asm volatile("fence.mbarrier_init.release.cluster;" ::: "memory");
  }
  if (tid == 0) STAMP(2, 6);
  asm volatile("barrier.cluster.arrive.relaxed.aligned;\nbarrier.cluster.wait.aligned;" ::: "memory");
  if (warp == 8 && elect_one()) tma2d_mc(sb + rank * 16384, &P.tmX, 0, mb * 256 + rank * 128, BAR(B_FULL1));
  if (tid == 256) STAMP(2, 7);

  if (warp < 8) {
    asm volatile("setmaxnreg.inc.sync.aligned.u32 224;");
    const int wg = warp >> 2, w = warp & 3, g = lane >> 2, q = lane & 3, t = tid & 127;
    const bool elect = (t == 0);
    const uint32_t s16 = (sb & 0x3FFFF) >> 4;
    uint32_t pq[2][16];
    ConvC K;
    {
      float acc[2][96];
      int st = 0, ph = 0;
#pragma unroll 1
      for (int kb = 0; kb < 14; kb++) {
        mbar_wait(BAR(B_FULL1 + st), ph);
        if (kb == 0 && elect) { STAMP(wg, 1); GSTAMP(wg, 26); }
        if (kb == 8 && elect) { STAMP(wg, 16); GSTAMP(wg, 25); }
        if (tid == 0) STAMP(2, 8 + kb);
        const uint32_t da = s16 + st * (STAGE_BYTES >> 4) + wg * 1024 + (1 << 16);
        const uint32_t db = s16 + st * (STAGE_BYTES >> 4) + 2048 + (512 << 16);
        wg_fence();
#pragma unroll
        for (int ks = 0; ks < 4; ks++) {
          wgmma_ss_n192<0, 1>(acc[0], dsc(da + ks * 2, SW128), dsc(db + ks * 128, SW128), (kb | ks) != 0);
          wgmma_ss_n192<0, 1>(acc[1], dsc(da + 512 + ks * 2, SW128), dsc(db + ks * 128, SW128), (kb | ks) != 0);
        }
        wg_commit();
        wg_wait<1>();
        if (kb > 0 && t < 2) mbar_arrive_cl(BAR(B_EMPTY1 + (st == 0 ? 2 : st - 1)), t);
        if (++st == 3) { st = 0; ph ^= 1; }
      }
#define TAIL_MMA(mt, stage) do { wg_fence(); _Pragma("unroll") for (int ks = 0; ks < 4; ks++) \
        wgmma_ss_n192<0, 1>(acc[mt], dsc(s16 + (stage) * (STAGE_BYTES >> 4) + wg * 1024 + (mt) * 512 + (1 << 16) + ks * 2, SW128), \
                            dsc(s16 + (stage) * (STAGE_BYTES >> 4) + 2048 + (512 << 16) + ks * 128, SW128), 1); wg_commit(); } while (0)
      mbar_wait(BAR(B_FULL1 + 2), 0);
      TAIL_MMA(0, 2);
      wg_wait<1>();
      if (elect) mbar_arrive(BAR(B_SFREE));
      mbar_wait(BAR(B_FULL1 + 0), 1);
      TAIL_MMA(0, 0);
      TAIL_MMA(1, 2);
      const uint32_t lrow = sb + wg * 16384 + (16 * w + 8 * ((lane >> 3) & 1) + (lane & 7)) * 128 + (((lane >> 4) ^ (lane & 7)) << 4);
#define E1K(mt, i) do { if (opaque_true()) { _Pragma("unroll") for (int j = (i); j < (i) + 2; j++) { \
          const float* a = &acc[mt][32 + 8 * j]; const float* b = a + 32; const uint32_t o = (lrow ^ (j * 32)) + (mt) * 8192; \
          stsm4(o + 2 * STAGE_BYTES, pk2(b[0], b[1]), pk2(b[2], b[3]), pk2(b[4], b[5]), pk2(b[6], b[7])); \
          stsm4(o, phi2(a[0], a[1]), phi2(a[2], a[3]), phi2(a[4], a[5]), phi2(a[6], a[7])); } } } while (0)
#define E1Q(mt) do { if (opaque_true()) { _Pragma("unroll") for (int i = 0; i < 16; i++) pq[mt][i] = phi2(acc[mt][2 * i], acc[mt][2 * i + 1]); } } while (0)
#define PK_READY(mt) do { fence_async(); __syncwarp(); if (lane == 0) mbar_arrive(BAR(B_PKRDY + (mt))); } while (0)
      wg_wait<1>();
      keep(acc[0]);
      if (elect) STAMP(wg, 18);
      E1K(0, 0);
      TAIL_MMA(1, 0);
      E1K(0, 2);
      if (elect) STAMP(wg, 19);
      PK_READY(0);
      wg_wait<0>();
      keep(acc[1]);
      asm volatile("setmaxnreg.dec.sync.aligned.u32 200;");
      if (elect) { STAMP(wg, 2); GSTAMP(wg, 27); }
      E1K(1, 0);
      E1K(1, 2);
      PK_READY(1);
      if (elect) STAMP(wg, 3);
      {
        const uint4* ct = (const uint4*)P.thr + t;
#pragma unroll
        for (int s = 0; s < 2; s++) { const uint4 u = ld_nc4(ct + s * 128); K.a1[s][0] = u.x; K.a1[s][1] = u.y; K.a1[s][2] = u.z; K.a1[s][3] = u.w; }
        const uint4 u = ld_nc4(ct + 2 * 128);
        K.wa[0] = u.x; K.wa[1] = u.y; K.wb[0] = u.z; K.wb[1] = u.w;
        K.sg = (lane & 4) ? 0xBC00BC00u : 0x3C003C00u;
      }
      if (CWAIT) mbar_wait(BAR(B_PKFREE), 0);
      if (elect) STAMP(wg, 4);
      E1Q(0);
      E1Q(1);
    }
    if (elect) STAMP(wg, 17);
    mbar_wait(BAR(B_H), 0);
    mbar_wait(BAR(B_PKRDY + 1), 0);
    if (elect) STAMP(wg, 5);
    {
      const uint32_t dfl = s16 + (OFF_F2F >> 4) + (8 << 16), dil = s16 + (OFF_F2I >> 4) + (8 << 16), d4l = s16 + (OFF_F4 >> 4) + (8 << 16);
      const uint32_t xl = s16 + (OFF_XT >> 4) + 4 * wg * (XT_STRIDE >> 4) + (8 << 16);
      const uint32_t hl = s16 + (OFF_H >> 4) + wg * 512 + (8 << 16);
      uint32_t vst = sb + wg * 8192 + w * 512 + lane * 16, vld = sb + wg * 8192 + w * 2048 + lane * 16;
      uint32_t ya = mapa(sb + OFF_XT + 4 * wg * XT_STRIDE + (2 * rank + (w & 1)) * 1024 + lane * 16, w >> 1);
      const uint32_t ybar = mapa(BAR(B_Y), w >> 1);
      asm volatile("" : "+r"(vst), "+r"(vld), "+r"(ya));
      uint32_t ux[16], uh[16], W[2][8], V0[8], V1[8], y[8], a[4][4];
      uint4* const ot = P.o + ((2 * mb + wg) * 16 + hq) * 1024 + (16 * w + g) * 8 + ((4 * rank + q) ^ g);
#define YOUT(i) do { if ((w >> 1) == rank) { \
          asm volatile("st.shared.v4.b32 [%0], {%1,%2,%3,%4};" ::"r"(ya + (i) * XT_STRIDE), "r"(y[0]), "r"(y[2]), "r"(y[4]), "r"(y[6]) : "memory"); \
          asm volatile("st.shared.v4.b32 [%0], {%1,%2,%3,%4};" ::"r"(ya + (i) * XT_STRIDE + 512), "r"(y[1]), "r"(y[3]), "r"(y[5]), "r"(y[7]) : "memory"); \
        } else { \
          mbar_wait(BAR(B_XFREE + 4 * wg + (i)), 0); \
          st_async4(ya + (i) * XT_STRIDE, y[0], y[2], y[4], y[6], ybar); \
          st_async4(ya + (i) * XT_STRIDE + 512, y[1], y[3], y[5], y[7], ybar); } } while (0)
      auto ocalc = [&](const int hh) {
        if (hh == 0) {
          if (elect) STAMP(wg, 8);
          mbar_wait(BAR(B_KV), 0);
          if (elect) STAMP(wg, 9);
        }
        float oa[2][20];
        wg_fence();
#pragma unroll
        for (int m = 0; m < 4; m++) {
          const uint32_t* p = &pq[m & 1][8 * hh + 4 * (m >> 1)];
          wgmma_rs_n40<1>(oa[m & 1], p[0], p[1], p[2], p[3], dsc(s16 + (OFF_KVB >> 4) + hh * 160 + (m >> 1) * 16 + (8 << 16), 32), m >> 1);
        }
        wg_commit();
        wg_wait<0>();
#pragma unroll
        for (int mt = 0; mt < 2; mt++) {
          float (&o)[20] = oa[mt];
          keep(o);
          const uint32_t den = hadd(pk2(o[16], o[18]), 0x35863586u);
#pragma unroll
          for (int r = 0; r < 2; r++) {
            const float ri = rcp_fast(__uint_as_float(r ? (den & 0xFFFF0000u) : (den << 16)));
            uint4 u;
            u.x = pk2(o[2 * r] * ri, o[2 * r + 1] * ri);
            u.y = pk2(o[4 + 2 * r] * ri, o[5 + 2 * r] * ri);
            u.z = pk2(o[8 + 2 * r] * ri, o[9 + 2 * r] * ri);
            u.w = pk2(o[12 + 2 * r] * ri, o[13 + 2 * r] * ri);
            st_cg4(ot + hh * 8 * 1024 + (64 * mt + 8 * r) * 8, u);
          }
        }
        __syncwarp();
        if (lane == 0) mbar_arrive(BAR(hh ? B_ODONE1 : B_ODONE));
        if (hh == 0 && elect) STAMP(wg, 10);
      };
      uint32_t X[4][2][8], H[4][2][8];
      conv_m1(K, ux, xl);
      conv_m1(K, uh, hl);
      wg_wait<1>(); keepu(ux);
      if (lane == 0) mbar_arrive_cl(BAR(B_XFREE + 4 * wg), rank ^ 1);
      conv_s2(K, ux, X[0], dfl);
      wg_wait<1>(); keepu(uh);
      conv_s2(K, uh, H[0], dfl);
#pragma unroll
      for (int i = 0; i < 4; i++) {
        const bool nx = i < 3;
        const int n = nx ? i + 1 : i;
        const uint32_t vo = (i & 1) ? OFF_H + (i >> 1) * 16384 : OFF_VP;
        if (2 * i == OCH) ocalc(0);
        if (2 * i == OCH + O1D) ocalc(1);
        if (nx) {
          if (n == 2) mbar_wait(BAR(B_H2), 0);
          conv_m1(K, ux, xl + n * (XT_STRIDE >> 4));
          conv_m1(K, uh, hl + (n >> 1) * 1024 + (n & 1) * 256);
        }
        if (2 * i != OCH && 2 * i != OCH + O1D) { if (nx) { if (i > 0) wg_wait<3>(); else wg_wait<2>(); } else wg_wait<1>(); }
        keepu(X[i][0]); keepu(X[i][1]); keepu(H[i][0]); keepu(H[i][1]);
        conv_win(K, X[i], W);
        conv_pw<0>(W, H[i], V0, dil);
        conv_pw<1>(W, H[i], V1, dil);
        wg_wait<2>();
        if (i > 0) { keepu(y); YOUT(i - 1); }
        if (2 * i + 1 == OCH) ocalc(0);
        if (2 * i + 1 == OCH + O1D) ocalc(1);
        if (nx) {
          keepu(ux); keepu(uh);
          if (lane == 0) mbar_arrive_cl(BAR(B_XFREE + 4 * wg + n), rank ^ 1);
          conv_s2(K, ux, X[n], dfl);
          wg_wait<1>();
        } else wg_wait<0>();
        keepu(V0); keepu(V1);
        conv_it<0>(K, V0, vst + vo);
        conv_it<1>(K, V1, vst + vo);
        bar_sync(1 + wg);
#pragma unroll
        for (int s = 0; s < 4; s++) ldsm4t(a[s], vld + vo + s * 512);
        if (nx) conv_s2(K, uh, H[n], dfl);
        conv_m4(y, a, d4l);
        if (i > 0 && lane < 2) mbar_arrive_cl(BAR(B_AFREE + i - 1), lane);
        if (elect && i < 3) STAMP(wg, i < 2 ? 6 + i : 9 + i);
      }
      wg_wait<0>(); keepu(y);
      YOUT(3);
      __syncwarp();
      if (lane == 0) mbar_arrive(BAR(B_Y));
      if (elect) STAMP(wg, 12);
    }
    {
      float acc[64];
#pragma unroll 1
      for (int kb = 0; kb < 16; kb++) {
        mbar_wait(BAR(B_FULL2 + kb), 0);
        if (kb == 0 && elect) { STAMP(wg, 13); GSTAMP(wg, 28); }
        const uint32_t da = s16 + ((uint32_t)(SLOT_A >> (4 * kb)) & 15) * 1024 + wg * 512 + (1 << 16);
        const uint32_t db = s16 + ((uint32_t)(SLOT_B >> (4 * kb)) & 15) * 1024 + (512 << 16);
        if (kb == HOLD2 && wg == 0) asm volatile("bar.sync 3, 256;" ::: "memory");
        wg_fence();
#pragma unroll
        for (int ks = 0; ks < 4; ks++) wgmma_ss_n128<0, 1>(acc, dsc(da + ks * 2, SW128), dsc(db + ks * 128, SW128), (kb | ks) != 0);
        wg_commit();
        if (HOLD2 < 16 && kb == 15 && wg == 1) asm volatile("bar.arrive 3, 256;" ::: "memory");
        wg_wait<1>();
        if (kb > 0 && kb < 13 && t < 2 && (kb <= 11 || t == rank)) mbar_arrive_cl(BAR(B_CONS2 + kb - 1), t);
      }
      wg_wait<0>();
      keep(acc);
      if (elect) { STAMP(wg, 14); GSTAMP(wg, 29); }
      mbar_wait(BAR(B_CONS2 + 11), 0);
      const uint32_t stg = sb + ((uint32_t)((wg ? SLOT_A : SLOT_B) >> 44) & 15) * 16384;
      const uint32_t lrow = stg + (16 * w + 8 * ((lane >> 3) & 1) + (lane & 7)) * 128 + (((lane >> 4) ^ (lane & 7)) << 4);
#pragma unroll
      for (int cp = 0; cp < 8; cp++) {
        const float* a = &acc[8 * cp];
        stsm4((lrow ^ ((cp & 3) * 32)) + (cp >> 2) * 8192, pk2(a[0], a[1]), pk2(a[2], a[3]), pk2(a[4], a[5]), pk2(a[6], a[7]));
      }
      fence_async();
      bar_sync(1 + wg);
      if (elect) {
        const int col = 1024 + 256 * cb + 128 * rank, row = 128 * rb + 64 * wg;
        tma2d_st(&P.tmOB, stg, col, row);
        tma2d_st(&P.tmOB, stg + 8192, col + 64, row);
        asm volatile("cp.async.bulk.commit_group;\ncp.async.bulk.wait_group.read 0;" ::: "memory");
        STAMP(wg, 15); GSTAMP(wg, 31); PDUMP(wg);
      }
    }
  } else {
    asm volatile("setmaxnreg.dec.sync.aligned.u32 56;");
    const int hw = warp - 9, g = lane >> 2, q = lane & 3;
#define sbar (bars + 8 * (B_STG - 18) + 16 * warp)
    if (warp == 8) {
      int st = 1, pp = 1;
      const uint8_t* pfx = (const uint8_t*)P.x + (mb * 256 + hp * 16 + (lane & 15)) * 2048;
      const uint8_t* pfw = (const uint8_t*)P.w + (mb * 8 + (lane & 7)) * 6144 + (lane >> 3) * 2048 + hp * 128;
#pragma unroll 1
      for (int kb = 1; kb < 16; kb++) {
        if (kb >= 3) mbar_wait(BAR(B_EMPTY1 + st), pp);
        const uint32_t sa = sb + st * STAGE_BYTES;
        if (elect_one()) {
          mbar_expect(BAR(B_FULL1 + st), STAGE_BYTES);
          tma2d_mc(sa + rank * 16384, &P.tmX, kb * 64, mb * 256 + rank * 128, BAR(B_FULL1 + st));
          tma3d(sa + 32768, &P.tmW, hp * 64, kb * 64, 0, BAR(B_FULL1 + st));
        }
        if (kb == 1 && lane == 0) STAMP(2, 24);
        if (PFD && kb >= 2) {
#pragma unroll 1
          for (int j = kb == 2 ? 3 : kb + PFD; j <= kb + PFD && j < 16; j++) {
            if (lane < 16) asm volatile("prefetch.global.L2 [%0];" ::"l"(pfx + j * 128));
            if (lane < 24) asm volatile("prefetch.global.L2 [%0];" ::"l"(pfw + j * (64 * 6144)));
          }
          if (kb >= QPF && kb < QPF + 8) asm volatile("prefetch.global.L2 [%0];" ::"l"((const uint8_t*)P.q + (blockIdx.x * 256 + (kb - QPF) * 32 + lane) * 128));
          if (kb >= 4)
            asm volatile("prefetch.global.L2 [%0];" ::"l"(kb < 12 ? (const uint8_t*)P.h + (blockIdx.x * 256 + (kb - 4) * 32 + lane) * 128
                                                                  : (const uint8_t*)P.wo + (blockIdx.x * 128 + (kb - 12) * 32 + lane) * 128));
        }
        if (++st == 3) { st = 0; pp ^= 1; }
      }
      if (lane == 0) STAMP(2, 1);
    } else {
      {
        const uint32_t clk0 = __shfl_sync(~0u, (uint32_t)clock(), 0), stg = sb + OFF_STG + hw * STG_STRIDE;
        const unsigned epoch = __shfl_sync(~0u, P.epoch[blockIdx.x], 0);
        const uint32_t tag = ~epoch & 1;
        uint32_t tap[2][4];
#pragma unroll
        for (int cg = 0; cg < 2; cg++) {
          const uint2 u = __ldg((const uint2*)(P.shift_k + (16 * cl + 8 * cg + g) * 4));
          tap[cg][0] = __byte_perm(u.x, 0, 0x1010); tap[cg][1] = __byte_perm(u.x, 0, 0x3232);
          tap[cg][2] = __byte_perm(u.y, 0, 0x1010); tap[cg][3] = __byte_perm(u.y, 0, 0x3232);
        }
        if (hw == 0 && lane < 8) *(float*)(smem + OFF_D + 4 * lane) = __bfloat162float(P.D[blockIdx.x * 8 + lane]);
        if (hw == 1) asm volatile("prefetch.global.L2 [%0];" ::"l"(P.thr + (lane + 32 * (blockIdx.x & 1)) * 32));
        if (hw == 0 && elect_one()) {
          *(volatile unsigned*)(smem + OFF_EPOCH) = epoch;
          mbar_expect(BAR(B_XRAW), 16384);
          mbar_expect(BAR(B_Y), 16384 + 64);
        }
        for (int i = hw * 32 + lane; i < 528; i += 96) st_tag4(P.part + (hp * 8 + mb) * 2176 + 4 * i, 0.f, 0.f, 0.f, 0.f, tag ^ 1);
        if (hw < 2 || lane < 2) st_tag4(P.kv + hp * 2176 + (4 * (hw < 2 ? 64 * mb + 32 * hw + lane : 512 + 2 * mb + lane)), 0.f, 0.f, 0.f, 0.f, tag ^ 1);
        if (lane == 0) STAMP(3, hw);
        const uint32_t xo = sb + OFF_XT + g * XT_STRIDE + rank * 2048 + q * 4;
        const int krow = 8 + (lane & 7) - (lane >> 3);
        const uint32_t ka = stg + krow * 32 + ((krow & 4) << 2), va = stg + 2304 + lane * 32 + ((lane & 4) << 2);
        int ph = 0, b = 0;
#pragma unroll 1
        for (int ci = hw - 3; ci < 16; ci += 3) {
          const uint32_t bo = b ? OFF_F2F - OFF_STG : 0, bn = b ? 0 : OFF_F2F - OFF_STG;
          if (ci + 3 < 16) {
            while (__any_sync(~0u, (uint32_t)clock() - clk0 < HSTART + (ci + 3) * PACE)) __nanosleep(64);
            if (elect_one()) {
              mbar_expect(sbar + 8 * (b ^ 1), 2304 + 2048);
              tma2d(stg + bn, &P.tmK, 16 * cl, 1024 * rank + 64 * (ci + 3) - 8, sbar + 8 * (b ^ 1));
              tma2d(stg + bn + 2304, &P.tmV, 16 * cl, 1024 * rank + 64 * (ci + 3), sbar + 8 * (b ^ 1));
            }
          }
          if (ci >= 0) {
            mbar_wait(sbar + 8 * b, (ph >> b) & 1);
            ph ^= 1 << b;
#pragma unroll 1
            for (int grp = 0; grp < 2; grp++) {
#pragma unroll
              for (int cg = 0; cg < 2; cg++) {
                const uint32_t dst = mapa(xo + (ci >> 3) * 1024 + ((ci & 7) * 4 + 2 * grp) * 16, cg), xbar = mapa(BAR(B_XRAW), cg);
                uint32_t vv[4], kk[4][4];
                ldsm4t(vv, (va ^ (cg * 16)) + bo + grp * 1024);
#pragma unroll
                for (int rg = 0; rg < 4; rg++) ldsm4t(kk[rg], (ka ^ (cg * 16)) + bo + grp * 1024 + rg * 256);
#pragma unroll
                for (int rg = 0; rg < 4; rg++)
                  vv[rg] = hmul(hadd(hadd(hadd(hmul(kk[rg][3], tap[cg][3]), hmul(kk[rg][2], tap[cg][2])), hmul(kk[rg][1], tap[cg][1])), hmul(kk[rg][0], tap[cg][0])), vv[rg]);
                if (cg == rank) {
#pragma unroll
                  for (int rg = 0; rg < 4; rg++) asm volatile("st.shared.b32 [%0], %1;" ::"r"(dst + (rg & 1) * 512 + (rg >> 1) * 16), "r"(vv[rg]) : "memory");
                } else {
#pragma unroll
                  for (int rg = 0; rg < 4; rg++) st_async(dst + (rg & 1) * 512 + (rg >> 1) * 16, vv[rg], xbar);
                }
              }
            }
          }
          b ^= 1;
        }
      }
      if (lane == 0) STAMP(3, 3 + hw);
      asm volatile("bar.sync 4, 96;" ::: "memory");
      if (hw == 0 && elect_one()) { mbar_expect(BAR(B_XT), 10240); bulk_ld(sb + OFF_F2F, P.img, 10240, BAR(B_XT)); }
      mbar_wait(BAR(B_XRAW), 0);
    }
#pragma unroll 1
    for (int n = hw < 0 ? 3 : 0; n < 4; n++) {
      const bool isH = n >= 3;
      const int c = isH ? (warp & 1) + 2 * (warp & 2) : hw + 3 * n;
      if (c < 8) {
        int ln;
        asm volatile("mov.u32 %0, %%laneid;" : "=r"(ln));
        uint8_t* dst = smem + (isH ? OFF_H + (c & 2) * 8192 + (c >> 2) * 8192 + (c & 1) * 4096 : OFF_XT + c * XT_STRIDE) + ((ln >> 4) * 512 + (ln & 15) * 16);
        const uint8_t* src0 = isH ? (const uint8_t*)P.h + (blockIdx.x * 8 + c) * 4096 + ((ln & 15) * 32 + (ln & 16)) : dst;
        const uint8_t* src1 = src0 + (isH ? 512 : 256);
        uint32_t v[32];
#pragma unroll
        for (int i = 0; i < 8; i++) {
          const uint4 u = *(const uint4*)(((i & 1) ? src1 : src0) + (i >> 1) * 1024);
          v[4 * i] = u.x; v[4 * i + 1] = u.y; v[4 * i + 2] = u.z; v[4 * i + 3] = u.w;
        }
        if (isH) mbar_wait(BAR(B_XT), 0);
        const int e = normalise(v, (isH && ln == 0) ? *(const float*)(smem + OFF_D + 4 * c) : 0.f);
        if (isH) {
          if (ln < 2) st_async(mapa(sb + OFF_SCALE + (8 * rank + c) * 4, ln), min(max(e + smem[OFF_EX + c] - 124, 1), 254) << 23, mapa(BAR(B_Y), ln));
          mbar_wait(BAR(B_SFREE), 0);
        } else if (ln == 0) smem[OFF_EX + c] = e;
#pragma unroll
        for (int i = 0; i < 8; i++)
          *(uint4*)(dst + (i >> 1) * 1024 + (i & 1) * 256) = make_uint4(v[4 * i], v[4 * i + 1], v[4 * i + 2], v[4 * i + 3]);
        if (n < 2 && elect_one()) {
          if (n == 0) mbar_expect(sbar, 4096);
          tma3d(sb + OFF_STG + 2048 * c, &P.tmQ, 16 * cl, 64 * rank, 2 * c, sbar);
        }
      }
      if (n >= 2) {
        fence_async();
        __syncwarp();
        if (lane == 0) { mbar_arrive(BAR(isH ? B_H : B_XT)); STAMP(3, (isH ? 17 : 13) + hw); }
      }
    }
    asm volatile("setmaxnreg.inc.sync.aligned.u32 104;");
    const unsigned epoch = *(volatile unsigned*)(smem + OFF_EPOCH);
    const uint32_t tag = ~epoch & 1;
    {
      const uint32_t s16 = (sb & 0x3FFFF) >> 4;
      const int t = tid & 127, c = 2 + (warp & 1) + 2 * (warp & 2);
      uint32_t v[32];
      const uint4* hp4 = (const uint4*)(P.h + (blockIdx.x * 8 + c) * 2048) + ((lane & 15) * 2 + (lane >> 4));
#pragma unroll
      for (int i = 0; i < 8; i++) { const uint4 u = ld_nc4(hp4 + i * 32); v[4 * i] = u.x; v[4 * i + 1] = u.y; v[4 * i + 2] = u.z; v[4 * i + 3] = u.w; }
      float kva[36];
#pragma unroll
      for (int mt = 0; mt < 2; mt++) {
        mbar_wait(BAR(B_PKRDY + mt), 0);
        wg_fence();
#pragma unroll
        for (int ks = 0; ks < 8; ks++) {
          const uint32_t o = (ks >> 2) * 1024 + mt * 512 + (ks & 3) * 128, vb = (2 * STAGE_BYTES >> 4) + o;
          wgmma_ss_n72<1, 1>(kva, dsc(s16 + o + (1 << 16), SW128), dsc(s16 + vb + (((OFF_ONES >> 4) - vb) << 16), SW128), (mt | ks) != 0);
        }
        wg_commit();
      }
      float* pdst = P.part + (hp * 8 + mb) * 2176 + t * 4;
      float* zdst = P.part + (hp * 8 + mb) * 2176 + 2048 + (t >> 1);
      asm volatile("" : "+l"(pdst), "+l"(zdst));
      wg_wait<0>();
      keep(kva);
      if (hw < 1) {
#pragma unroll
        for (int c = 0; c < 4; c++) st_tag4(pdst + c * 512, kva[4 * c], kva[4 * c + 1], kva[4 * c + 2], kva[4 * c + 3], tag);
      } else {
#pragma unroll
        for (int c = 4; c < 8; c++) st_tag4(pdst + (c - 4) * 512, kva[4 * c], kva[4 * c + 1], kva[4 * c + 2], kva[4 * c + 3], tag);
      }
      const float z2 = __shfl_down_sync(~0u, kva[32], 4), z3 = __shfl_down_sync(~0u, kva[34], 4);
      if (!(lane & 7)) st_tag4(zdst, kva[32], kva[34], z2, z3, tag);
      if (lane == 0) mbar_arrive(BAR(B_PKFREE));
      if (hw == 0 && lane == 0) STAMP(3, 24);
      const int e = normalise(v, lane == 0 ? *(const float*)(smem + OFF_D + 4 * c) : 0.f);
      uint8_t* dst = smem + OFF_H + 16384 + (warp & 3) * 4096 + (lane >> 4) * 512 + (lane & 15) * 16;
#pragma unroll
      for (int i = 0; i < 8; i++)
        *(uint4*)(dst + (i >> 1) * 1024 + (i & 1) * 256) = make_uint4(v[4 * i], v[4 * i + 1], v[4 * i + 2], v[4 * i + 3]);
      if (lane < 2) st_async(mapa(sb + OFF_SCALE + (8 * rank + c) * 4, lane), min(max(e + smem[OFF_EX + c] - 124, 1), 254) << 23, mapa(BAR(B_Y), lane));
      fence_async();
      __syncwarp();
      if (lane == 0) mbar_arrive(BAR(B_H2));
    }
    if (warp == 8) {
#define SLOT(tab, kb) (sb + ((uint32_t)((tab) >> (4 * (kb))) & 15) * 16384)
#define LOAD_B(kb) tma4d(SLOT(SLOT_B, kb), &P.tmWo, 0, ((kb) >> 3) * 32, 2 * ((kb) & 7), 4 * cb + 2 * rank, BAR(B_FULL2 + (kb)))
#define LOAD_A(kb) bulk_ld_mc(SLOT(SLOT_A, kb) + rank * 8192, P.o + (rb * 16 + (kb)) * 1024 + rank * 512, 8192, BAR(B_FULL2 + (kb)))
      mbar_wait(BAR(B_PKFREE), 0);
      {
        const uint32_t c0 = clock();
#pragma unroll 1
        for (int i = 0; i < 14; i++) {
          const int kb = i >> 1;
          while (__any_sync(~0u, (uint32_t)clock() - c0 < i * BPACE)) __nanosleep(32);
          if (elect_one()) {
            if (!(i & 1)) mbar_expect(BAR(B_FULL2 + kb), 16384);
            tma4d(SLOT(SLOT_B, kb) + (i & 1) * 8192, &P.tmWo1, 0, 0, 2 * kb, 4 * cb + 2 * rank + (i & 1), BAR(B_FULL2 + kb));
            if (i == 0) mbar_expect(BAR(B_Q), 8192);
            if (i < 4) tma3d(sb + OFF_SPARE + 2048 * i, &P.tmQ, 16 * cl, 64 * rank + 32 * (i >> 1), 2 * ((i + 6) & 7), BAR(B_Q));
          }
        }
      }
      if (lane == 0) STAMP(2, 2);
      mbar_wait(BAR(B_AFREE), 0);
      if (elect_one()) mbar_expect(BAR(B_FULL2), 16384);
      {
        const uint32_t dst = SLOT(SLOT_A, 0) + rank * 8192;
        const uint4* src = P.o + rb * 16 * 1024 + rank * 512;
        poll_ge(&P.ocnt[rb * 32], 16 * (epoch + 1));
        asm volatile("fence.proxy.async.global;" ::: "memory");
        if (lane == 0) STAMP(2, 3);
        if (elect_one()) bulk_ld_mc(dst, src, 8192, BAR(B_FULL2));
        if (lane == 0) STAMP(3, 23);
      }
#pragma unroll 1
      for (int kb = 1; kb < 7; kb++) {
        mbar_wait(BAR(kb < 3 ? B_AFREE + kb : B_CONS2 + ((kb - 3) >> 1)), 0);
        if (elect_one()) { mbar_expect(BAR(B_FULL2 + kb), 16384); LOAD_A(kb); }
      }
#pragma unroll 1
      for (int kb = 7; kb < 16; kb++) {
        mbar_wait(BAR(B_CONS2 + kb - 5), 0);
        if (kb == 8) mbar_wait(BAR(B_O1RDY), 0);
        if (elect_one()) { mbar_expect(BAR(B_FULL2 + kb), 32768); LOAD_A(kb); LOAD_B(kb); }
      }
      if (lane == 0) { P.epoch[blockIdx.x] = epoch + 1; STAMP(2, 5); PDUMP(2); }
    } else {
      if (hw == 0 && lane == 0) STAMP(3, 20);
      if (PD1) __nanosleep(PD1);
      {
        const int pi = hw < 2 ? 64 * mb - 288 + tid : 512 + 2 * mb + (lane & 1);
        const float* psrc = P.part + hp * 8 * 2176 + 4 * pi;
        uint4 f[8];
#pragma unroll
        for (int p = 0; p < 8; p++) f[p] = ld_rlx4(psrc + p * 2176);
        if (!opaque_true()) __trap();
#pragma unroll 1
        for (int n = 0; __any_sync(~0u, stale8(f, tag) & 1); n++) {
#pragma unroll
          for (int p = 0; p < 8; p++) ld_stale4(f[p], psrc + p * 2176, tag);
          if (n > SPIN_LIMIT) __trap();
        }
        float s0 = 0.f, s1 = 0.f, s2 = 0.f, s3 = 0.f;
#pragma unroll
        for (int p = 0; p < 8; p++) { s0 += __uint_as_float(f[p].x); s1 += __uint_as_float(f[p].y); s2 += __uint_as_float(f[p].z); s3 += __uint_as_float(f[p].w); }
        if (hw < 2 || lane < 2) st_tag4(P.kv + hp * 2176 + (4 * pi), s0, s1, s2, s3, tag);
      }
      if (lane == 0 && hw == 0) STAMP(3, 8);
      if (hw == 2) {
        unsigned* cnt = P.ocnt + (2 * mb + lane) * 32;
#pragma unroll 1
        for (int hh = 0; hh < 2; hh++) {
          mbar_wait(BAR(hh ? B_ODONE1 : B_ODONE), 0);
          if (lane < 2) asm volatile("red.release.gpu.global.add.u32 [%0], 1;" ::"l"(cnt + hh * 512) : "memory");
          if (lane == 0) STAMP(3, hh ? 6 : 7);
        }
        poll_ge(&P.ocnt[512 + rb * 32], 16 * (epoch + 1));
        asm volatile("fence.proxy.async.global;" ::: "memory");
        if (lane == 0) { mbar_arrive(BAR(B_O1RDY)); STAMP(2, 4); }
        __syncwarp();
      } else {
        if (PD2) __nanosleep(PD2);
        const int t = tid - 288;
        uint4 f[8];
        const float* src = P.kv + hp * 2176 + (4 * t);
        const float* zsrc = P.kv + hp * 2176 + (2048 + (t & 48) + 2 * (lane & 6));
        uint4 zp = ld_rlx4(zsrc);
#pragma unroll
        for (int p = 0; p < 8; p++) f[p] = ld_rlx4(src + 4 * ((p & 3) * 128 + (p >> 2) * 64));
        if (!opaque_true()) __trap();
#pragma unroll 1
        for (int n = 0; __any_sync(~0u, (stale8(f, tag) | (zp.x ^ tag)) & 1); n++) {
          ld_stale4(zp, zsrc, tag);
#pragma unroll
          for (int p = 0; p < 8; p++) ld_stale4(f[p], src + 4 * ((p & 3) * 128 + (p >> 2) * 64), tag);
          if (n > SPIN_LIMIT) __trap();
        }
#define PK2U(a, b) pk2(__uint_as_float(a), __uint_as_float(b))
        const uint32_t zf = (lane & 1) ? ((lane & 8) ? zp.w : zp.z) : ((lane & 8) ? zp.y : zp.x);
        const uint32_t zz = PK2U(zf, zf);
        *(uint4*)(smem + OFF_KVB + hw * 2560 + 2048 + lane * 16) = make_uint4(zz, zz, zz, zz);
        if (!opaque_true()) __trap();
#pragma unroll
        for (int hh = 0; hh < 2; hh++) {
          const uint4* ff = &f[4 * hh];
          uint8_t* dst = smem + OFF_KVB + hh * 2560 + q * 512 + (16 * hw + g) * 16;
          *(uint4*)dst = make_uint4(PK2U(ff[0].x, ff[0].y), PK2U(ff[1].x, ff[1].y), PK2U(ff[2].x, ff[2].y), PK2U(ff[3].x, ff[3].y));
          *(uint4*)(dst + 128) = make_uint4(PK2U(ff[0].z, ff[0].w), PK2U(ff[1].z, ff[1].w), PK2U(ff[2].z, ff[2].w), PK2U(ff[3].z, ff[3].w));
        }
        fence_async();
        __syncwarp();
        if (lane == 0) { mbar_arrive(BAR(B_KV)); if (hw == 0) STAMP(3, 9); }
      }
#define QBUF(ci) (sb + 2048 * (ci) + ((ci) < 6 ? OFF_STG : (ci) < 10 ? OFF_SPARE - 6 * 2048 : OFF_F2F - 10 * 2048))
      mbar_wait(BAR(B_Y), 0);
      if (elect_one()) {
        mbar_expect(sbar + 8, 4096);
#pragma unroll 1
        for (int ci = hw ? hw + 9 : 12; ci < 16; ci += 3) tma3d(QBUF(ci), &P.tmQ, 16 * cl, 64 * rank + 32, 2 * (ci & 7), sbar + 8);
      }
      mbar_wait(BAR(B_Q), 0);
      mbar_wait(sbar, hw == 0);
      {
        const float2 sc0 = *(const float2*)(smem + OFF_SCALE + 8 * q), sc1 = *(const float2*)(smem + OFF_SCALE + 32 + 8 * q);
        const uint32_t yl = sb + OFF_XT + (lane & 7) * XT_STRIDE + (lane >> 3) * 16;
#pragma unroll 1
        for (int ci = hw; ci < 16; ci += 3) {
          const uint32_t qb = QBUF(ci);
          if (ci >= 10) mbar_wait(sbar + 8, 1);
#pragma unroll 1
          for (int nl = 0; nl < 2; nl++) {
            uint32_t yy[2][4], qq[2][4];
            const uint32_t qa = qb + lane * 32 + ((lane & 4) << 2) + nl * 1024;
#pragma unroll
            for (int cg = 0; cg < 2; cg++) { ldsm4t(yy[cg], yl + cg * 2048 + (2 * ci + nl) * 64); ldsm4(qq[cg], qa ^ (cg * 16)); }
#pragma unroll
            for (int cg = 0; cg < 2; cg++) {
              const float2 sc = cg ? sc1 : sc0;
#pragma unroll
              for (int m = 0; m < 4; m++) {
                const float2 f = __half22float2(*(const __half2*)&yy[cg][m]);
                qq[cg][m] = hmul(qq[cg][m], pk2(f.x * sc.x, f.y * sc.y));
              }
              stsm4(qa ^ (cg * 16), qq[cg][0], qq[cg][1], qq[cg][2], qq[cg][3]);
            }
          }
          fence_async();
          __syncwarp();
          if (elect_one()) tma3d_st(&P.tmOA, qb, 16 * cl, 64 * rank + 32 * (ci >> 3), 2 * (ci & 7));
        }
        asm volatile("cp.async.bulk.commit_group;\ncp.async.bulk.wait_group.read 0;" ::: "memory");
      }
      if (lane == 0) STAMP(3, 10 + hw);
    }
  }
}

typedef CUresult (*EncodeFn)(CUtensorMap*, CUtensorMapDataType, cuuint32_t, void*, const cuuint64_t*, const cuuint64_t*,
                             const cuuint32_t*, const cuuint32_t*, CUtensorMapInterleave, CUtensorMapSwizzle,
                             CUtensorMapL2promotion, CUtensorMapFloatOOBfill);

static void enc(EncodeFn fn, CUtensorMap* m, const void* p, int rank, const cuuint64_t* dims, const cuuint64_t* strides,
                const cuuint32_t* box, CUtensorMapSwizzle swz, CUtensorMapL2promotion promo) {
  cuuint32_t es[4] = {1, 1, 1, 1};
  fn(m, CU_TENSOR_MAP_DATA_TYPE_BFLOAT16, rank, (void*)p, dims, strides, box, es, CU_TENSOR_MAP_INTERLEAVE_NONE, swz, promo,
     CU_TENSOR_MAP_FLOAT_OOB_FILL_NONE);
}

extern "C" void kernel_launch(void* const* d_in, const int* in_sizes, int n_in, void* d_out, int out_size) {
  void* fp = nullptr;
  cudaDriverEntryPointQueryResult qr;
  cudaGetDriverEntryPoint("cuTensorMapEncodeTiled", &fp, cudaEnableDefault, &qr);
  EncodeFn fn = (EncodeFn)fp;
  Params P;
  P.shift_k = (const __nv_bfloat16*)d_in[3]; P.h = (const __nv_bfloat16*)d_in[4]; P.D = (const __nv_bfloat16*)d_in[5];
  P.q = (const __nv_bfloat16*)d_in[0];
  cudaGetSymbolAddress((void**)&P.part, g_part); cudaGetSymbolAddress((void**)&P.kv, g_kv); cudaGetSymbolAddress((void**)&P.o, g_o);
  cudaGetSymbolAddress((void**)&P.ocnt, g_ocnt); cudaGetSymbolAddress((void**)&P.epoch, g_epoch);
  cudaGetSymbolAddress((void**)&P.thr, c_thr); cudaGetSymbolAddress((void**)&P.img, c_img);
  P.x = (const __nv_bfloat16*)d_in[6]; P.w = (const __nv_bfloat16*)d_in[7]; P.wo = (const __nv_bfloat16*)d_in[8];
  const CUtensorMapSwizzle S128 = CU_TENSOR_MAP_SWIZZLE_128B, S32 = CU_TENSOR_MAP_SWIZZLE_32B;
  const CUtensorMapL2promotion P0 = CU_TENSOR_MAP_L2_PROMOTION_NONE, P128 = CU_TENSOR_MAP_L2_PROMOTION_L2_128B;
  { cuuint64_t d[2] = {1024, 2048}, s[1] = {2048}; cuuint32_t b[2] = {64, 128}; enc(fn, &P.tmX, d_in[6], 2, d, s, b, S128, P128); }
  { cuuint64_t d[3] = {1024, 1024, 3}, s[2] = {6144, 2048}; cuuint32_t b[3] = {64, 64, 3}; enc(fn, &P.tmW, d_in[7], 3, d, s, b, S128, P128); }
  { cuuint64_t d[4] = {64, 64, 16, 16}, s[3] = {2048, 131072, 128}; cuuint32_t b[4] = {64, 32, 2, 2}; enc(fn, &P.tmWo, d_in[8], 4, d, s, b, S128, P128); }
  { cuuint64_t d[4] = {64, 64, 16, 16}, s[3] = {2048, 131072, 128}; cuuint32_t b[4] = {64, 32, 2, 1}; enc(fn, &P.tmWo1, d_in[8], 4, d, s, b, S128, P128); }
  { cuuint64_t d[2] = {1024, 2048}, s[1] = {2048}; cuuint32_t b[2] = {16, 72}; enc(fn, &P.tmK, d_in[1], 2, d, s, b, S32, PKV); }
  { cuuint64_t d[2] = {1024, 2048}, s[1] = {2048}; cuuint32_t b[2] = {16, 64}; enc(fn, &P.tmV, d_in[2], 2, d, s, b, S32, PKV); }
  { cuuint64_t d[3] = {1024, 128, 16}, s[2] = {32768, 2048}; cuuint32_t b[3] = {16, 32, 2}; enc(fn, &P.tmQ, d_in[0], 3, d, s, b, S32, PKV); }
  { cuuint64_t d[3] = {1024, 128, 16}, s[2] = {65536, 4096}; cuuint32_t b[3] = {16, 32, 2}; enc(fn, &P.tmOA, d_out, 3, d, s, b, S32, P0); }
  { cuuint64_t d[2] = {2048, 2048}, s[1] = {4096}; cuuint32_t b[2] = {64, 64}; enc(fn, &P.tmOB, d_out, 2, d, s, b, S128, P0); }
  cudaFuncSetAttribute(fused_kernel, cudaFuncAttributeMaxDynamicSharedMemorySize, SMEM_TOTAL);
  fused_kernel<<<128, 384, SMEM_TOTAL>>>(P);
}
```

```cpp
#include <cuda_runtime.h>
#include <cuda_bf16.h>
#include <cuda_fp16.h>
#include <cuda.h>
#include <stdint.h>

template<int TA, int TB, int SA=1> __device__ __forceinline__ void wgmma_ss_n192(float (&d)[96], uint64_t da, uint64_t db, int scale_d) {
  asm volatile("{\n.reg .pred p;\nsetp.ne.b32 p, %98, 0;\n"
    "wgmma.mma_async.sync.aligned.m64n192k16.f32.bf16.bf16 {%0, %1, %2, %3, %4, %5, %6, %7, %8, %9, %10, %11, %12, %13, %14, %15, %16, %17, %18, %19, %20, %21, %22, %23, %24, %25, %26, %27, %28, %29, %30, %31, %32, %33, %34, %35, %36, %37, %38, %39, %40, %41, %42, %43, %44, %45, %46, %47, %48, %49, %50, %51, %52, %53, %54, %55, %56, %57, %58, %59, %60, %61, %62, %63, %64, %65, %66, %67, %68, %69, %70, %71, %72, %73, %74, %75, %76, %77, %78, %79, %80, %81, %82, %83, %84, %85, %86, %87, %88, %89, %90, %91, %92, %93, %94, %95}, %96, %97, p, %101, 1, %99, %100;\n}\n"
    : "+f"(d[0]), "+f"(d[1]), "+f"(d[2]), "+f"(d[3]), "+f"(d[4]), "+f"(d[5]), "+f"(d[6]), "+f"(d[7]), "+f"(d[8]), "+f"(d[9]), "+f"(d[10]), "+f"(d[11]), "+f"(d[12]), "+f"(d[13]), "+f"(d[14]), "+f"(d[15]), "+f"(d[16]), "+f"(d[17]), "+f"(d[18]), "+f"(d[19]), "+f"(d[20]), "+f"(d[21]), "+f"(d[22]), "+f"(d[23]), "+f"(d[24]), "+f"(d[25]), "+f"(d[26]), "+f"(d[27]), "+f"(d[28]), "+f"(d[29]), "+f"(d[30]), "+f"(d[31]), "+f"(d[32]), "+f"(d[33]), "+f"(d[34]), "+f"(d[35]), "+f"(d[36]), "+f"(d[37]), "+f"(d[38]), "+f"(d[39]), "+f"(d[40]), "+f"(d[41]), "+f"(d[42]), "+f"(d[43]), "+f"(d[44]), "+f"(d[45]), "+f"(d[46]), "+f"(d[47]), "+f"(d[48]), "+f"(d[49]), "+f"(d[50]), "+f"(d[51]), "+f"(d[52]), "+f"(d[53]), "+f"(d[54]), "+f"(d[55]), "+f"(d[56]), "+f"(d[57]), "+f"(d[58]), "+f"(d[59]), "+f"(d[60]), "+f"(d[61]), "+f"(d[62]), "+f"(d[63]), "+f"(d[64]), "+f"(d[65]), "+f"(d[66]), "+f"(d[67]), "+f"(d[68]), "+f"(d[69]), "+f"(d[70]), "+f"(d[71]), "+f"(d[72]), "+f"(d[73]), "+f"(d[74]), "+f"(d[75]), "+f"(d[76]), "+f"(d[77]), "+f"(d[78]), "+f"(d[79]), "+f"(d[80]), "+f"(d[81]), "+f"(d[82]), "+f"(d[83]), "+f"(d[84]), "+f"(d[85]), "+f"(d[86]), "+f"(d[87]), "+f"(d[88]), "+f"(d[89]), "+f"(d[90]), "+f"(d[91]), "+f"(d[92]), "+f"(d[93]), "+f"(d[94]), "+f"(d[95])
    : "l"(da), "l"(db), "r"(scale_d), "n"(TA), "n"(TB), "n"(SA));
}
template<int TA, int TB, int SA=1> __device__ __forceinline__ void wgmma_ss_n128(float (&d)[64], uint64_t da, uint64_t db, int scale_d) {
  asm volatile("{\n.reg .pred p;\nsetp.ne.b32 p, %66, 0;\n"
    "wgmma.mma_async.sync.aligned.m64n128k16.f32.bf16.bf16 {%0, %1, %2, %3, %4, %5, %6, %7, %8, %9, %10, %11, %12, %13, %14, %15, %16, %17, %18, %19, %20, %21, %22, %23, %24, %25, %26, %27, %28, %29, %30, %31, %32, %33, %34, %35, %36, %37, %38, %39, %40, %41, %42, %43, %44, %45, %46, %47, %48, %49, %50, %51, %52, %53, %54, %55, %56, %57, %58, %59, %60, %61, %62, %63}, %64, %65, p, %69, 1, %67, %68;\n}\n"
    : "+f"(d[0]), "+f"(d[1]), "+f"(d[2]), "+f"(d[3]), "+f"(d[4]), "+f"(d[5]), "+f"(d[6]), "+f"(d[7]), "+f"(d[8]), "+f"(d[9]), "+f"(d[10]), "+f"(d[11]), "+f"(d[12]), "+f"(d[13]), "+f"(d[14]), "+f"(d[15]), "+f"(d[16]), "+f"(d[17]), "+f"(d[18]), "+f"(d[19]), "+f"(d[20]), "+f"(d[21]), "+f"(d[22]), "+f"(d[23]), "+f"(d[24]), "+f"(d[25]), "+f"(d[26]), "+f"(d[27]), "+f"(d[28]), "+f"(d[29]), "+f"(d[30]), "+f"(d[31]), "+f"(d[32]), "+f"(d[33]), "+f"(d[34]), "+f"(d[35]), "+f"(d[36]), "+f"(d[37]), "+f"(d[38]), "+f"(d[39]), "+f"(d[40]), "+f"(d[41]), "+f"(d[42]), "+f"(d[43]), "+f"(d[44]), "+f"(d[45]), "+f"(d[46]), "+f"(d[47]), "+f"(d[48]), "+f"(d[49]), "+f"(d[50]), "+f"(d[51]), "+f"(d[52]), "+f"(d[53]), "+f"(d[54]), "+f"(d[55]), "+f"(d[56]), "+f"(d[57]), "+f"(d[58]), "+f"(d[59]), "+f"(d[60]), "+f"(d[61]), "+f"(d[62]), "+f"(d[63])
    : "l"(da), "l"(db), "r"(scale_d), "n"(TA), "n"(TB), "n"(SA));
}
template<int TA, int TB, int SA=1> __device__ __forceinline__ void wgmma_ss_n72(float (&d)[36], uint64_t da, uint64_t db, int scale_d) {
  asm volatile("{\n.reg .pred p;\nsetp.ne.b32 p, %38, 0;\n"
    "wgmma.mma_async.sync.aligned.m64n72k16.f32.bf16.bf16 {%0, %1, %2, %3, %4, %5, %6, %7, %8, %9, %10, %11, %12, %13, %14, %15, %16, %17, %18, %19, %20, %21, %22, %23, %24, %25, %26, %27, %28, %29, %30, %31, %32, %33, %34, %35}, %36, %37, p, %41, 1, %39, %40;\n}\n"
    : "+f"(d[0]), "+f"(d[1]), "+f"(d[2]), "+f"(d[3]), "+f"(d[4]), "+f"(d[5]), "+f"(d[6]), "+f"(d[7]), "+f"(d[8]), "+f"(d[9]), "+f"(d[10]), "+f"(d[11]), "+f"(d[12]), "+f"(d[13]), "+f"(d[14]), "+f"(d[15]), "+f"(d[16]), "+f"(d[17]), "+f"(d[18]), "+f"(d[19]), "+f"(d[20]), "+f"(d[21]), "+f"(d[22]), "+f"(d[23]), "+f"(d[24]), "+f"(d[25]), "+f"(d[26]), "+f"(d[27]), "+f"(d[28]), "+f"(d[29]), "+f"(d[30]), "+f"(d[31]), "+f"(d[32]), "+f"(d[33]), "+f"(d[34]), "+f"(d[35])
    : "l"(da), "l"(db), "r"(scale_d), "n"(TA), "n"(TB), "n"(SA));
}
template<int TB, int SA=1> __device__ __forceinline__ void wgmma_rs_n40(float (&d)[20], uint32_t a0, uint32_t a1, uint32_t a2, uint32_t a3, uint64_t db, int scale_d) {
  asm volatile("{\n.reg .pred p;\nsetp.ne.b32 p, %25, 0;\n"
    "wgmma.mma_async.sync.aligned.m64n40k16.f32.bf16.bf16 {%0, %1, %2, %3, %4, %5, %6, %7, %8, %9, %10, %11, %12, %13, %14, %15, %16, %17, %18, %19}, {%20, %21, %22, %23}, %24, p, %27, 1, %26;\n}\n"
    : "+f"(d[0]), "+f"(d[1]), "+f"(d[2]), "+f"(d[3]), "+f"(d[4]), "+f"(d[5]), "+f"(d[6]), "+f"(d[7]), "+f"(d[8]), "+f"(d[9]), "+f"(d[10]), "+f"(d[11]), "+f"(d[12]), "+f"(d[13]), "+f"(d[14]), "+f"(d[15]), "+f"(d[16]), "+f"(d[17]), "+f"(d[18]), "+f"(d[19])
    : "r"(a0), "r"(a1), "r"(a2), "r"(a3), "l"(db), "r"(scale_d), "n"(TB), "n"(SA));
}
template<int TB> __device__ __forceinline__ void wgmma_hrs_n64(uint32_t (&d)[16], uint32_t a0, uint32_t a1, uint32_t a2, uint32_t a3, uint64_t db, int scale_d) {
  asm volatile("{\n.reg .pred p;\nsetp.ne.b32 p, %21, 0;\n"
    "wgmma.mma_async.sync.aligned.m64n64k16.f16.f16.f16 {%0, %1, %2, %3, %4, %5, %6, %7, %8, %9, %10, %11, %12, %13, %14, %15}, {%16, %17, %18, %19}, %20, p, 1, 1, %22;\n}\n"
    : "+r"(d[0]), "+r"(d[1]), "+r"(d[2]), "+r"(d[3]), "+r"(d[4]), "+r"(d[5]), "+r"(d[6]), "+r"(d[7]), "+r"(d[8]), "+r"(d[9]), "+r"(d[10]), "+r"(d[11]), "+r"(d[12]), "+r"(d[13]), "+r"(d[14]), "+r"(d[15])
    : "r"(a0), "r"(a1), "r"(a2), "r"(a3), "l"(db), "r"(scale_d), "n"(TB));
}
template<int TB> __device__ __forceinline__ void wgmma_hrs_n32(uint32_t (&d)[8], uint32_t a0, uint32_t a1, uint32_t a2, uint32_t a3, uint64_t db, int scale_d) {
  asm volatile("{\n.reg .pred p;\nsetp.ne.b32 p, %13, 0;\n"
    "wgmma.mma_async.sync.aligned.m64n32k16.f16.f16.f16 {%0, %1, %2, %3, %4, %5, %6, %7}, {%8, %9, %10, %11}, %12, p, 1, 1, %14;\n}\n"
    : "+r"(d[0]), "+r"(d[1]), "+r"(d[2]), "+r"(d[3]), "+r"(d[4]), "+r"(d[5]), "+r"(d[6]), "+r"(d[7])
    : "r"(a0), "r"(a1), "r"(a2), "r"(a3), "l"(db), "r"(scale_d), "n"(TB));
}

__device__ __align__(128) const uint32_t c_thr[1536] = {
  0x33fb33ff,0xa49c9de4,0x33273352,0xaf2cae76,0x33e233f1,0xa96ca7bd,0x32c432f7,0xb045afdd,0x33b733cf,0xac3eaaf7,0x3250328c,0xb0eab099,
  0x3378339a,0xadbcacff,0x31cd3211,0xb182b137,0x33d033fb,0xaadea46a,0x299e2d17,0xb3e0b396,0x32fb337a,0xafd2adb1,0xa78b1f76,0xb3f2b3ff,
  0x318b3254,0xb1c5b0e5,0xae6bac32,0xb354b3b8,0x2f4230a3,0xb321b285,0xb133b040,0xb215b2c7,0x337c33f2,0xada5a759,0xb179afc8,0xb1d6b2fe,
  0x31463293,0xb204b08e,0xb394b2ba,0xad23b055,0x2b402f4e,0xb3cbb31e,0xb3e4b3f9,0x293ba533,0xac269c52,0xb3bab400,0xb258b357,0x30e02e5f,
  0x330133e5,0xafbda922,0xb3f3b3c9,0x2727ab59,0x2deb314a,0xb36fb200,0xb194b32f,0x31bc2f0a,0xacdb2084,0xb39fb3ff,0xa565aea4,0x33f93347,
  0xb2b6b0db,0xb05ab25c,0x30892c1a,0x329733bc,0x326033d4,0xb0d6aa94,0xb00ab29b,0x32e83084,0x20e82f64,0xb3feb318,0x2d8da597,0x338133f8,
  0xb1fcae48,0xb14fb35c,0x339031b8,0x2d3a3199,0xb3e6b3ae,0x2909ac7b,0x32d133f4,0xb030a6f5,0x319d33bf,0xb1b3ac02,0x2e3ca874,0x335e33ec,
  0xacc32b89,0xb3a3b3c6,0x33f83276,0x25c930b7,0xb3dcb1f8,0xaa01b154,0x30653335,0xb2b0aef4,0xb107b383,0x32392d81,0xafa6214d,0xb307b3fe,
  0x30bc33a5,0xb273acb7,0x33c5311b,0x2ba23229,0xb0cc94b6,0xb267b400,0x30153360,0xb2e1ae31,0xb385b3ab,0x2d76ac93,0xb166a691,0xb1e7b3f5,
  0x22deb06a,0x33fd32ac,0xb337b3da,0x2ee8aa19,0x2f853387,0xb310ad6a,0x322d33fe,0xb1162216,0xb2a9abd3,0xb06fb3c2,0xb07428a6,0xb2a5b3ea,
  0xb111b3e9,0x323128be,0xb30db3c3,0x2f90abba,0x31aa227a,0x31a633fd,0x2e25ad5e,0x33633389,0x2d6a3365,0xb387ae1a,0xa21631aa,0xb3feb1a6,
  0xb3c2af85,0xabd3b310,0xb3eab22d,0x28a6b116,0xa8beb2a9,0x33e9306f,0x2bbab074,0x33c332a5,0x33fd3111,0x227a3231,0x3389330d,0xad5e2f90,
  0x2a63333f,0xb3d7aec6,0xb2a2a1b1,0xb07ab3fe,0xb3f7b158,0x25fbb1f4,0xacb7b38b,0x33a52d52,0x2e0eb025,0x336832d8,0x340030bc,0x14b63273,
  0x323533c0,0xb10c2beb,0xac9330cc,0xb3abb267,0x23433316,0xb3fdaf6f,0xb38eb225,0x2d46b11f,0xb342b29e,0x2ebbb07f,0x31e3aa7c,0x316b33d6,
  0x3264a6c3,0x30d133f5,0x2c0233ac,0xb3bfac87,0x28f0336a,0xb3e7ae02,0xb3c6b19d,0x2b89b1b3,0xa59732e8,0xb3f8b00a,0xaccfb3ed,0x33a1285b,
  0xb1b8b381,0x3199ad8d,0x336c31df,0xadf73170,0x33f42d3a,0x26f53390,0xb30423a7,0xafb2b3fc,0xb05f3030,0xb2b3b2d1,0x29e8b27a,0x33dd30b2,
  0xab5932b6,0xb3c9b05a,0x30adb089,0x327e3297,0xaf0ab3f3,0x332fa727,0x240633b0,0xb3fcac6f,0x33473194,0xaea431bc,0xb174b359,0x31daae54,
  0xb3bca565,0xac1ab3f9,0x33ee2f59,0xa842331b,0xaddf3281,0xb371b0a8,0x34002b40,0x1c5233cb,0xa759b3ef,0x33f22829,0xb2fe2c26,0xafc8b3ba,
  0x308e337c,0xb2932da5,0x3055b179,0x32ba31d6,0xb31eb146,0x2f4eb204,0xa5333394,0xb3f9ad23,0xaff33249,0xb2f1b0f3,0x30e532fb,0xb2542fd2,
  0x2b28b373,0x33cc2dd4,0xb285b18b,0x30a3b1c5,0x246a33fa,0xb3fba500,0x33962f42,0xad173321,0xadb1b3d0,0x337aaade,0xb3ffa99e,0x1f76b3e0,
  0xb0ee320d,0xb24db13c,0xac4b3398,0xb3b5ad0b,0x304ab289,0x32c1309e,0x2985b3ce,0x33e12b0f,0xaf3732f4,0xb324afe8,0xa4ce33f0,0xb3faa7ef,
  0x2dc8b34f,0x33762e82,0x9de4b3ff,0x33ff1ead,0xb1c931cd,0xb186b182,0xb3762e82,0xadc8b34f,0x324db13c,0x30ee320d,0x33b5ad0b,0x2c4b3398,
  0xb2c1309e,0xb04ab289,0xb3e12b0f,0xa985b3ce,0x3324afe8,0x2f3732f4,0x33faa7ef,0x24ce33f0,0xb285318b,0xb0a3b1c5,0xb2c7ae6b,0x3040b354,
  0x3396af42,0x2d173321,0x31413133,0xb2093215,0xb3ff299e,0x9f76b3e0,0xae8db2bd,0x334cb050,0x33b8278b,0xac3233f2,0x281033b3,0xb3ef2c57,
  0xb31e3146,0xaf4eb204,0xa533b394,0x33f9ad23,0x3400ab40,0x9c5233cb,0xae5f33e4,0xb357a93b,0xb2feac26,0x2fc8b3ba,0x3245b258,0x30f830e0,
  0x30553179,0xb2ba31d6,0xb3df2e99,0xa9b6b34a,0xb39230fd,0xad2fb241,0x3200b301,0x314a2fbd,0x337f1b11,0xad993400,0xb3ff2deb,0xa084b36f,
  0xb005b129,0x32ebb21d,0x325c2cdb,0xb0db339f,0xa92233de,0xb3e529cf,0xab59b2b6,0x33c9b05a,0xb3dd30b2,0xa9e8b27a,0x33d4ab71,0xaa9433c8,
  0x32212c0e,0xb12433bd,0xaf64b0d6,0x3318b260,0x197fb345,0x3400aeaf,0xae4833fe,0xb35c20e8,0xb23d3332,0xb102aeff,0x33aeb14f,0x2c7b31fc,
  0xb3fe3065,0xa14db2b0,0x2ebb307f,0xb342329e,0x300f2fa6,0xb2e53307,0x30d1b3f5,0x326426c3,0x302ab400,0x32d517db,0xb3e72e02,0x28f0b36a,
  0xb3fd2f6f,0x2343b316,0x2d46311f,0xb38e3225,0xb3f53015,0x2691b2e1,0xaf9b33eb,0xb30a288d,0x2a193166,0xb3da31e7,0x33d7aec6,0xaa63333f,
  0x3313b337,0x2f7a2ee8,0xa5fbb1f4,0x33f7b158,0xb1a1a8d7,0x31afb3e8,0xb36832d8,0xae0eb025,0xb3c22f85,0x2bd3b310,0xb3ea322d,0xa8a6b116,
  0xa8be32a9,0xb3e9306f,0x2bba3074,0xb3c332a5,0x33fdb111,0xa27a3231,0x3389b30d,0x2d5e2f90,0xa216b1aa,0x33feb1a6,0xaed2ae25,0x333db363,
  0xb3652edd,0x2e1ab33a,0xb1aa227a,0x31a6b3fd,0xaf853387,0xb3102d6a,0xb22d33fe,0xb116a216,0x32a9abd3,0xb06f33c2,0x307428a6,0xb2a533ea,
  0x3111b3e9,0x3231a8be,0x330db3c3,0x2f902bba,0xb2e12e31,0x3015b360,0x288db1a1,0x33ebb1af,0xb1e733f5,0xb1662691,0xb33f2f9b,0x2ec6b30a,
  0x2ee82a19,0xb33733da,0xb15833d7,0xb1f42a63,0x33e8b313,0x28d72f7a,0x302525fb,0xb2d833f7,0xb2392d81,0x3107b383,0x3307b3fe,0x2fa6214d,
  0xb35e33ec,0xae3ca874,0x97dbb00f,0x3400b2e5,0xa5c930b7,0xb3f83276,0xb316302a,0x2f6fb2d5,0x32b0aef4,0xb0653335,0xb29e33fd,0xb07f2343,
  0xb1702ccf,0x31dfb3a1,0x3345b124,0xaeaf3221,0xb3fc336c,0xa3a7adf7,0x3332b400,0x2eff997f,0xb0b23304,0xb27a2fb2,0x2b71b102,0x33c8b23d,
  0x2c0e29e8,0xb3bd33dd,0xb0d62a94,0x3260b3d4,0xb0892c1a,0x3297b3bc,0x2aad2842,0xb3d333ee,0xb3b0327e,0x2c6fb0ad,0x3241b035,0xb0fd32ce,
  0xb35933fc,0xae542406,0x3400b392,0x1b112d2f,0xaf5931da,0xb31b3174,0x321db37f,0x3129ad99,0xaf152ac6,0x332cb3d2,0xb1463293,0xb204308e,
  0xb281312e,0x30a8b219,0xab402f4e,0xb3cb331e,0xb3ef3371,0x2829addf,0x2c269c52,0xb3ba3400,0xb37c33f2,0xada52759,0x3179afc8,0xb1d632fe,
  0xacf32953,0x339cb3e3,0xb3fa33cc,0x2500ab28,0xb0942f21,0x3290b32a,0xb3d033fb,0xaade246a,0xb249317d,0x30f3b1d2,0xb2fb337a,0xafd22db1,
  0xb37332f1,0x2dd4aff3,0xb18b3254,0xb1c530e5,0xa96c27bd,0x33e2b3f1,0xb0452fdd,0x32c4b2f7,0xac3e2af7,0x33b7b3cf,0xb0ea3099,0x3250b28c,
  0xadbc2cff,0x3378b39a,0xb1823137,0x31cdb211,0xaf2c2e76,0x3327b352,0xb20d31c9,0x313cb186,0x313c3186,0xb20db1c9,0x2d0b2dc8,0xb398b376,
  0x309e30ee,0xb289b24d,0x2b0f2c4b,0xb3ceb3b5,0x2fe8304a,0xb2f4b2c1,0x27ef2985,0xb3f0b3e1,0x2e822f37,0xb34fb324,0x1ead24ce,0xb3ffb3fa,
  0xb2bdb209,0xb050b141,0xb290b32a,0x30942f21,0xb3b3b34c,0xac57ae8d,0xb0f3b1d2,0x3249317d,0xb400b3ef,0x1d1ba810,0xadd4aff3,0x337332f1,
  0xb39cb3e3,0x2cf32953,0xa500ab28,0x33fa33cc,0xae99b0f8,0x334a3245,0x33ff33b2,0x201f2c63,0x2438a9b6,0x33fc33df,0x332c33d2,0xaf15aac6,
  0x303a2ce7,0x32cb339e,0x30a83219,0xb281b12e,0x32ee31c0,0x2ffe3190,0x28292ddf,0xb3efb371,0x33b0327e,0x2c6f30ad,0xb241b035,0xb0fdb2ce,
  0x335933fc,0xae54a406,0xb400b392,0x1b11ad2f,0x2f5931da,0xb31bb174,0xb21db37f,0x31292d99,0xaaad2842,0xb3d3b3ee,0xa9cfb005,0x33de32eb,
  0x285b305f,0xb3edb2b3,0x2c0ea9e8,0x33bd33dd,0xb170accf,0xb1dfb3a1,0x33453124,0x2eaf3221,0xb3fcb36c,0x23a7adf7,0x33323400,0xaeff997f,
  0xb0b2b304,0x327a2fb2,0x2b713102,0xb3c8b23d,0xb400b2e5,0x17dbb00f,0x2e023264,0xb36ab0d1,0xaf6fb2d5,0x3316302a,0xb11fa8f0,0xb225b3e7,
  0x307f2343,0x329e33fd,0xb3d6b38e,0x2a7cad46,0x33f53342,0xa6c32ebb,0xac87b1e3,0x33ac316b,0x28d7af7a,0x33e83313,0xb2d8b3f7,0x3025a5fb,
  0x33eb31af,0x288d31a1,0x2bebae0e,0x33c03368,0x2ec6330a,0xb33faf9b,0x33fe3235,0x21b1310c,0xb1f4aa63,0xb158b3d7,0x2d5232a2,0xb38bb07a,
  0x33a7333d,0xacab2ed2,0x33f63162,0x262d31eb,0xaa4b301a,0xb3d8b2de,0x2a32326b,0xb3d9b0c7,0xb3f6b26f,0x265fb0c1,0xb3a9b020,0xac9fb2db,
  0x0e48b15d,0x340031f0,0xae1ab33a,0x33652edd,0xaed22e25,0xb33db363,0xb1eb0e48,0xb162b400,0xb2deb3a7,0x301aacab,0xb0c7b3f6,0x326b262d,
  0x30c1aa4b,0x326f33d8,0x32db2a32,0x302033d9,0x31f033f6,0xb15d265f,0x2edd33a9,0xb33aac9f,0xb2acb385,0x306aad76,0x2a19b166,0x33da31e7,
  0x3229a2de,0x311b33fd,0x33133337,0xaf7a2ee8,0x2e3133c5,0xb360aba2,0xb1a128d7,0xb1afb3e8,0xb3f5b015,0xa691b2e1,0xaf9bb3eb,0x330a288d,
  0x3154acc3,0x31f833a3,0x2ef433f8,0xb335a5c9,0x2d8133dc,0xb383aa01,0xb3feb065,0x214db2b0,0xb3ecb107,0x2874b239,0x300fafa6,0x32e53307,
  0x30b7ae3c,0x3276335e,0x302a3400,0xb2d517db,0x312433bd,0xb2212c0e,0xb318b260,0x2f64b0d6,0xb400aeaf,0x997fb345,0x335c20e8,0x2e4833fe,
  0x3102aeff,0x323d3332,0xac7b31fc,0xb3aeb14f,0x2a9433c8,0xb3d4ab71,0xb084b3e6,0x329ba909,0xb2ce2aad,0xb035b3d3,0x33e529cf,0x292233de,
  0x2d2fb241,0x339230fd,0xb14a2fbd,0xb200b301,0x2d993400,0xb37f1b11,0x2084b36f,0x33ff2deb,0xb2ebb21d,0x3005b129,0x30db339f,0xb25c2cdb,
  0xae5fb3e4,0x3357a93b,0xb190303a,0xb1c0b2cb,0x32453258,0xb0f830e0,0x2c63b2ee,0x33b22ffe,0xb3dfae99,0x29b6b34a,0x2ac633ff,0xb3d2a01f,
  0x339ea438,0x2ce733fc,0xb12eb32c,0x3219af15,0x33b8a78b,0x2c3233f2,0x2810b3b3,0x33ef2c57,0xb2c72e6b,0xb040b354,0x29533400,0xb3e31d1b,
  0x3141b133,0x32093215,0xaf21b39c,0x332aacf3,0xae8d32bd,0xb34cb050,0x317d3290,0xb1d23094,0x27bd33fb,0xb3f1249c,0x2fdd3327,0xb2f72f2c,
  0xaaf7b3e2,0x33cfa96c,0xb099b2c4,0x328cb045,0x2cff33b7,0xb39a2c3e,0x31373250,0xb21130ea,0xae76b378,0x3352adbc,0xb1c9b1cd,0x3186b182,
  0xb3ff1ead,0x1de4b3ff,0xb352adbc,0x2e76b378,0x33f1249c,0xa7bd33fb,0x32f72f2c,0xafdd3327,0xb3cfa96c,0x2af7b3e2,0xb28cb045,0x3099b2c4,
  0x339a2c3e,0xacff33b7,0x321130ea,0xb1373250,0x2953b400,0x33e31d1b,0x33ccadd4,0x2b283373,0xaf21339c,0xb32aacf3,0xb3fb2500,0x246ab3fa,
  0x317db290,0x31d23094,0x337a2ade,0xadb133d0,0xb2f130f3,0xaff3b249,0xb254afd2,0x30e5b2fb,0x339e2438,0xace733fc,0xb12e332c,0xb219af15,
  0xb190b03a,0x31c0b2cb,0x3371b0a8,0x2ddf3281,0x2c6332ee,0xb3b22ffe,0xb3f22829,0x2759b3ef,0x2ac6b3ff,0x33d2a01f,0x32932da5,0xb08e337c,
  0xaf0a33f3,0xb32fa727,0x2406b3b0,0x33fcac6f,0x3347b194,0x2ea431bc,0xb1743359,0xb1daae54,0xb3bc2565,0x2c1ab3f9,0x33eeaf59,0x2842331b,
  0x30ad3089,0xb27e3297,0xb2ceaaad,0x3035b3d3,0xb29ba909,0x3084b3e6,0x305f3030,0xb2b332d1,0x259732e8,0xb3f8300a,0x2ccfb3ed,0x33a1a85b,
  0x31b8b381,0x31992d8d,0xb36c31df,0xadf7b170,0xb3f42d3a,0x26f5b390,0x330423a7,0xafb233fc,0x316bb3d6,0x31e32a7c,0xb3832a01,0x2d81b3dc,
  0xb3bf2c87,0x2c02b3ac,0x28743239,0xb3ec3107,0x2b8931b3,0xb3c6319d,0x3276b35e,0x30b72e3c,0x31f8b3a3,0x31542cc3,0xb33525c9,0x2ef4b3f8,
  0x310c2beb,0xb23533c0,0x33abb267,0x2c9330cc,0x307ab3fe,0x32a2a1b1,0xb06aad76,0x32acb385,0xb3a52d52,0x2cb7b38b,0xb11b33fd,0xb229a2de,
  0x94b63273,0xb40030bc,0x3360aba2,0xae3133c5,0xb2de33a7,0xb01aacab,0xb0c733f6,0xb26b262d,0x30c12a4b,0xb26f33d8,0x32dbaa32,0xb02033d9,
  0x31f0b3f6,0x315d265f,0x2eddb3a9,0x333aac9f,0xb1eb8e48,0x3162b400,0xb3872e1a,0x2d6ab365,0xae25ad5e,0x3363b389,0x8e48b15d,0x3400b1f0,
  0xb3a7333d,0xacabaed2,0xb3f63162,0x262db1eb,0x2a4b301a,0xb3d832de,0xaa32326b,0xb3d930c7,0x33f6b26f,0x265f30c1,0x33a9b020,0xac9f32db,
  0x33c0b368,0x2beb2e0e,0x30cc94b6,0xb2673400,0x21b1b10c,0x33feb235,0x3385b3ab,0x2d762c93,0xb38b307a,0x2d52b2a2,0xa2deb06a,0x33fdb2ac,
  0xb0bc33a5,0xb2732cb7,0xb3c5311b,0x2ba2b229,0x26c32ebb,0xb3f53342,0xb3ac316b,0x2c87b1e3,0x336ab0d1,0xae023264,0xb19d33bf,0xb1b32c02,
  0x3225b3e7,0x311fa8f0,0x2cc32b89,0xb3a333c6,0xaa7cad46,0x33d6b38e,0x33dcb1f8,0xaa013154,0xb3fe3318,0x20e8af64,0x3381b3f8,0x2d8d2597,
  0xb14f335c,0xb1fc2e48,0x2d3ab199,0x3390b1b8,0x29092c7b,0xb3e633ae,0xb03026f5,0x32d1b3f4,0x32e8b084,0xb00a329b,0xb3ed32b3,0x285bb05f,
  0x29cfb005,0x33deb2eb,0xb05a325c,0xb2b630db,0xafbd2922,0x3301b3e5,0x27272b59,0xb3f333c9,0xb36f3200,0x2debb14a,0x31bcaf0a,0xb194332f,
  0xb39f33ff,0xacdba084,0x33f9b347,0xa5652ea4,0x3394b2ba,0xad233055,0xa438a9b6,0x33fcb3df,0x33e4b3f9,0x293b2533,0xb03a2ce7,0x32cbb39e,
  0x3258b357,0x30e0ae5f,0xb2ee31c0,0x2ffeb190,0x2e99b0f8,0x334ab245,0xb3ff33b2,0x201fac63,0xaf4230a3,0xb3213285,0x3133b040,0xb21532c7,
  0xa99e2d17,0xb3e03396,0x32bdb209,0xb0503141,0x278b1f76,0xb3f233ff,0x33b3b34c,0xac572e8d,0x2e6bac32,0xb35433b8,0x3400b3ef,0x1d1b2810,
  0xb289324d,0x309eb0ee,0xb3ce33b5,0x2b0fac4b,0xb2f432c1,0x2fe8b04a,0xb3f033e1,0x27efa985,0xb34f3324,0x2e82af37,0xb3ff33fa,0x1eada4ce,
  0xb3983376,0x2d0badc8,0xb3fb33ff,0xa49c1de4,0x351c35f6,0xac93a617,0xb8a3b93c,0x308d2a16,0x32f43448,0xb160afa5,0xb6a4b7fe,0x353a3389,
  0x2fa53160,0xb448b2f4,0xb389b53a,0x37fe36a4,0x26172c93,0xb5f6b51c,0xaa16b08d,0x393c38a3,0x34c3358c,0xac47a5b2,0xb85fb8f3,0x304229b1,
  0x327e33fd,0xb106af26,0xb63cb785,0x34e7330f,0x2f263106,0xb3fdb27e,0xb30fb4e7,0x3785363c,0x25b22c47,0xb58cb4c3,0xa9b1b042,0x38f3385f,
  0x346a3523,0xabf6a54d,0xb81ab8a8,0x2fef294d,0x3209336b,0xb0acaea7,0xb5d4b70a,0x34933294,0x2ea730ac,0xb36bb209,0xb294b493,0x370a35d4,
  0x254d2bf6,0xb523b46a,0xa94dafef,0x38a8381a,0x341334bc,0xab5fa4e9,0xb7a6b85a,0x2f5928e8,0x319432da,0xb052ae28,0xb56ab68d,0x343e3219,
  0x2e283052,0xb2dab194,0xb219b43e,0x368d356a,0x24e92b5f,0xb4bcb413,0xa8e8af59,0x385a37a6,0x33783456,0xaac8a484,0xb715b80a,0x2ec32884,
  0x3120324a,0xaff2ada9,0xb4ffb60e,0x33d3319e,0x2da92ff2,0xb24ab120,0xb19eb3d3,0x360e34ff,0x24842ac8,0xb456b378,0xa884aec3,0x380a3715,
  0x32cd33e3,0xaa31a420,0xb682b76f,0x2e2d281f,0x30ac31bb,0xaf3fad2a,0xb493b58d,0x33283122,0x2d2a2f3f,0xb1bbb0ac,0xb122b328,0x358d3493,
  0x24202a31,0xb3e3b2cd,0xa81fae2d,0x376f3682,0x3223331c,0xa999a376,0xb5ebb6c6,0x2d972776,0x3039312d,0xae8dacac,0xb426b50b,0x327c30a6,
  0x2cac2e8d,0xb12db039,0xb0a6b27c,0x350b3426,0x23762999,0xb31cb223,0xa776ad97,0x36c635eb,0x317a3257,0xa902a2ad,0xb552b61a,0x2d0026ad,
  0x2f8c309f,0xaddcac2e,0xb371b487,0x31cf3029,0x2c2e2ddc,0xb09faf8c,0xb029b1cf,0x34873371,0x22ad2902,0xb257b17a,0xa6adad00,0x361a3552,
  0x30d23194,0xa86ba1e4,0xb4b7b56a,0x2c6a25e4,0x2ea73012,0xad2aab5f,0xb294b402,0x31222f59,0x2b5f2d2a,0xb012aea7,0xaf59b122,0x34023294,
  0x21e4286b,0xb194b0d2,0xa5e4ac6a,0x356a34b7,0x302c30d2,0xa7a9a11b,0xb41ab4b7,0x2ba7251b,0x2dc22f0c,0xac79aa63,0xb1b6b2f7,0x30742e5f,
  0x2a632c79,0xaf0cadc2,0xae5fb074,0x32f731b6,0x211b27a9,0xb0d2b02c,0xa51baba7,0x34b7341a,0x2f0c3012,0xa67ba052,0xb2f7b402,0x2a7a2452,
  0x2cde2df5,0xab91a967,0xb0d7b1e8,0x2f8b2d65,0x29672b91,0xadf5acde,0xad65af8b,0x31e830d7,0x2052267b,0xb012af0c,0xa452aa7a,0x340232f7,
  0x2dc22ea7,0xa54d9f12,0xb1b6b294,0x294d2311,0x2bf62cde,0xaa31a86b,0xafefb0d7,0x2e2d2c6a,0x286b2a31,0xacdeabf6,0xac6aae2d,0x30d72fef,
  0x1f12254d,0xaea7adc2,0xa311a94d,0x329431b6,0x2c792d2a,0xa4209d7f,0xb074b122,0x281f217f,0x2a312b91,0xa8d0a6e0,0xae2daf8b,0x2cce2ade,
  0x26e028d0,0xab91aa31,0xaadeacce,0x2f8b2e2d,0x1d7f2420,0xad2aac79,0xa17fa81f,0x31223074,0x2a632b5f,0xa1e49bdb,0xae5faf59,0x25e41fdb,
  0x286b2967,0xa6e0a4e9,0xac6aad65,0x2ade28e8,0x24e926e0,0xa967a86b,0xa8e8aade,0x2d652c6a,0x1bdb21e4,0xab5faa63,0x9fdba5e4,0x2f592e5f,
  0x27a9286b,0x9f1298b6,0xaba7ac6a,0x23111cb6,0x254d267b,0xa420a1e4,0xa94daa7a,0x281f25e4,0x21e42420,0xa67ba54d,0xa5e4a81f,0x2a7a294d,
  0x18b61f12,0xa86ba7a9,0x9cb6a311,0x2c6a2ba7,0x211b21e4,0x98b69248,0xa51ba5e4,0x1cb61648,0x1f122052,0x9d7f9bdb,0xa311a452,0x217f1fdb,
  0x1bdb1d7f,0xa0529f12,0x9fdba17f,0x24522311,0x124818b6,0xa1e4a11b,0x96489cb6,0x25e4251b,0xa11ba1e4,0x18b61248,0x251b25e4,0x9cb69648,
  0x9f12a052,0x1d7f1bdb,0x23112452,0xa17f9fdb,0x9bdb9d7f,0x20521f12,0x1fdb217f,0xa452a311,0x924898b6,0x21e4211b,0x16481cb6,0xa5e4a51b,
  0xa7a9a86b,0x1f1218b6,0x2ba72c6a,0xa3119cb6,0xa54da67b,0x242021e4,0x294d2a7a,0xa81fa5e4,0xa1e4a420,0x267b254d,0x25e4281f,0xaa7aa94d,
  0x98b69f12,0x286b27a9,0x1cb62311,0xac6aaba7,0xaa63ab5f,0x21e41bdb,0x2e5f2f59,0xa5e49fdb,0xa86ba967,0x26e024e9,0x2c6a2d65,0xaadea8e8,
  0xa4e9a6e0,0x2967286b,0x28e82ade,0xad65ac6a,0x9bdba1e4,0x2b5f2a63,0x1fdb25e4,0xaf59ae5f,0xac79ad2a,0x24201d7f,0x30743122,0xa81fa17f,
  0xaa31ab91,0x28d026e0,0x2e2d2f8b,0xacceaade,0xa6e0a8d0,0x2b912a31,0x2ade2cce,0xaf8bae2d,0x9d7fa420,0x2d2a2c79,0x217f281f,0xb122b074,
  0xadc2aea7,0x254d1f12,0x31b63294,0xa94da311,0xabf6acde,0x2a31286b,0x2fef30d7,0xae2dac6a,0xa86baa31,0x2cde2bf6,0x2c6a2e2d,0xb0d7afef,
  0x9f12a54d,0x2ea72dc2,0x2311294d,0xb294b1b6,0xaf0cb012,0x267b2052,0x32f73402,0xaa7aa452,0xacdeadf5,0x2b912967,0x30d731e8,0xaf8bad65,
  0xa967ab91,0x2df52cde,0x2d652f8b,0xb1e8b0d7,0xa052a67b,0x30122f0c,0x24522a7a,0xb402b2f7,0xb02cb0d2,0x27a9211b,0x341a34b7,0xaba7a51b,
  0xadc2af0c,0x2c792a63,0x31b632f7,0xb074ae5f,0xaa63ac79,0x2f0c2dc2,0x2e5f3074,0xb2f7b1b6,0xa11ba7a9,0x30d2302c,0x251b2ba7,0xb4b7b41a,
  0xb0d2b194,0x286b21e4,0x34b7356a,0xac6aa5e4,0xaea7b012,0x2d2a2b5f,0x32943402,0xb122af59,0xab5fad2a,0x30122ea7,0x2f593122,0xb402b294,
  0xa1e4a86b,0x319430d2,0x25e42c6a,0xb56ab4b7,0xb17ab257,0x290222ad,0x3552361a,0xad00a6ad,0xaf8cb09f,0x2ddc2c2e,0x33713487,0xb1cfb029,
  0xac2eaddc,0x309f2f8c,0x302931cf,0xb487b371,0xa2ada902,0x3257317a,0x26ad2d00,0xb61ab552,0xb223b31c,0x29992376,0x35eb36c6,0xad97a776,
  0xb039b12d,0x2e8d2cac,0x3426350b,0xb27cb0a6,0xacacae8d,0x312d3039,0x30a6327c,0xb50bb426,0xa376a999,0x331c3223,0x27762d97,0xb6c6b5eb,
  0xb2cdb3e3,0x2a312420,0x3682376f,0xae2da81f,0xb0acb1bb,0x2f3f2d2a,0x3493358d,0xb328b122,0xad2aaf3f,0x31bb30ac,0x31223328,0xb58db493,
  0xa420aa31,0x33e332cd,0x281f2e2d,0xb76fb682,0xb378b456,0x2ac82484,0x3715380a,0xaec3a884,0xb120b24a,0x2ff22da9,0x34ff360e,0xb3d3b19e,
  0xada9aff2,0x324a3120,0x319e33d3,0xb60eb4ff,0xa484aac8,0x34563378,0x28842ec3,0xb80ab715,0xb413b4bc,0x2b5f24e9,0x37a6385a,0xaf59a8e8,
  0xb194b2da,0x30522e28,0x356a368d,0xb43eb219,0xae28b052,0x32da3194,0x3219343e,0xb68db56a,0xa4e9ab5f,0x34bc3413,0x28e82f59,0xb85ab7a6,
  0xb46ab523,0x2bf6254d,0x381a38a8,0xafefa94d,0xb209b36b,0x30ac2ea7,0x35d4370a,0xb493b294,0xaea7b0ac,0x336b3209,0x32943493,0xb70ab5d4,
  0xa54dabf6,0x3523346a,0x294d2fef,0xb8a8b81a,0xb4c3b58c,0x2c4725b2,0x385f38f3,0xb042a9b1,0xb27eb3fd,0x31062f26,0x363c3785,0xb4e7b30f,
  0xaf26b106,0x33fd327e,0x330f34e7,0xb785b63c,0xa5b2ac47,0x358c34c3,0x29b13042,0xb8f3b85f,0xb51cb5f6,0x2c932617,0x38a3393c,0xb08daa16,
  0xb2f4b448,0x31602fa5,0x36a437fe,0xb53ab389,0xafa5b160,0x344832f4,0x3389353a,0xb7feb6a4,0xa617ac93,0x35f6351c,0x2a16308d,0xb93cb8a3,
};
__device__ __align__(128) const uint32_t c_img[2560] = {
  0x326d31ed,0x333b32dd,0x33c33388,0x33fe33ea,0x33c331ed,0x31ed33c3,0xa8b22d64,0xb33bb0c4,0x33ea31ed,0xad64301d,0xb2ddb388,0x315fa8b2,
  0x32dd31ed,0xb3feabc6,0x326dad64,0xad64326d,0x30c431ed,0xaed7b2dd,0x2bc63388,0xa248b3ea,0x2bc631ed,0x315fb3c3,0xb3ea2d64,0x2ed730c4,
  0xa8b231ed,0x3388b01d,0x301db388,0xb1ed28b2,0xb01d31ed,0x22482bc6,0x30c4ad64,0x3388b26d,0x33ea33fe,0x338833c3,0x32dd333b,0x31ed326d,
  0xb2ddb3fe,0xa248b01d,0x326d2ed7,0x338833ea,0x30c433fe,0xb33babc6,0xabc6b33b,0x33fe30c4,0xabc6b3fe,0x31ed32dd,0xb3eaaed7,0x333ba8b2,
  0xa8b233fe,0x2d64b3c3,0xb01d333b,0x315fb26d,0x301db3fe,0xb3fe301d,0x30c42ed7,0x2d64b3ea,0xb26d33fe,0x2ed72bc6,0x33c3b33b,0xa248b0c4,
  0x33c3b3fe,0x315fb2dd,0x28b2aed7,0xaed728b2,0xb0c4b15f,0xaed7b01d,0xabc6ad64,0xa248a8b2,0xabc6b15f,0x315f2bc6,0x33ea3388,0x2ed7326d,
  0x28b2b15f,0x338832dd,0xb01d2d64,0xb1edb3ea,0x301db15f,0x224833c3,0xb0c4b388,0x338830c4,0x326db15f,0xb33b301d,0x33c3ad64,0xb3fe28b2,
  0x33c3b15f,0xb1edabc6,0xa8b23388,0x333bb26d,0x33eab15f,0x2d64b2dd,0xb2dd2d64,0xb15f33ea,0x32ddb15f,0x33feb3c3,0x326db388,0x2d64b0c4,
  0x28b22248,0x2d642bc6,0x301d2ed7,0x315f30c4,0xb01da248,0xb3feb2dd,0xb0c4b33b,0x2d64a8b2,0x326d2248,0x2ed733c3,0xb3c3aed7,0xa248b26d,
  0xb3c3a248,0x315fb01d,0xa8b2333b,0xaed7b3ea,0x33ea2248,0xb388abc6,0x32dd2ed7,0xb1edb0c4,0xb2dda248,0x224832dd,0x326db33b,0xb38828b2,
  0x30c42248,0x333bb3c3,0xabc6aed7,0xb3fe326d,0xabc6a248,0xb1ed301d,0xb3ea333b,0xb33b33ea,0xb26d31ed,0xb33b32dd,0xb3c33388,0xb3fe33ea,
  0xb3c331ed,0xb1ed33c3,0x28b22d64,0x333bb0c4,0xb3ea31ed,0x2d64301d,0x32ddb388,0xb15fa8b2,0xb2dd31ed,0x33feabc6,0xb26dad64,0x2d64326d,
  0xb0c431ed,0x2ed7b2dd,0xabc63388,0x2248b3ea,0xabc631ed,0xb15fb3c3,0x33ea2d64,0xaed730c4,0x28b231ed,0xb388b01d,0xb01db388,0x31ed28b2,
  0x301d31ed,0xa2482bc6,0xb0c4ad64,0xb388b26d,0xb3ea33fe,0xb38833c3,0xb2dd333b,0xb1ed326d,0x32ddb3fe,0x2248b01d,0xb26d2ed7,0xb38833ea,
  0xb0c433fe,0x333babc6,0x2bc6b33b,0xb3fe30c4,0x2bc6b3fe,0xb1ed32dd,0x33eaaed7,0xb33ba8b2,0x28b233fe,0xad64b3c3,0x301d333b,0xb15fb26d,
  0xb01db3fe,0x33fe301d,0xb0c42ed7,0xad64b3ea,0x326d33fe,0xaed72bc6,0xb3c3b33b,0x2248b0c4,0xb3c3b3fe,0xb15fb2dd,0xa8b2aed7,0x2ed728b2,
  0x30c4b15f,0x2ed7b01d,0x2bc6ad64,0x2248a8b2,0x2bc6b15f,0xb15f2bc6,0xb3ea3388,0xaed7326d,0xa8b2b15f,0xb38832dd,0x301d2d64,0x31edb3ea,
  0xb01db15f,0xa24833c3,0x30c4b388,0xb38830c4,0xb26db15f,0x333b301d,0xb3c3ad64,0x33fe28b2,0xb3c3b15f,0x31edabc6,0x28b23388,0xb33bb26d,
  0xb3eab15f,0xad64b2dd,0x32dd2d64,0x315f33ea,0xb2ddb15f,0xb3feb3c3,0xb26db388,0xad64b0c4,0xa8b22248,0xad642bc6,0xb01d2ed7,0xb15f30c4,
  0x301da248,0x33feb2dd,0x30c4b33b,0xad64a8b2,0xb26d2248,0xaed733c3,0x33c3aed7,0x2248b26d,0x33c3a248,0xb15fb01d,0x28b2333b,0x2ed7b3ea,
  0xb3ea2248,0x3388abc6,0xb2dd2ed7,0x31edb0c4,0x32dda248,0xa24832dd,0xb26db33b,0x338828b2,0xb0c42248,0xb33bb3c3,0x2bc6aed7,0x33fe326d,
  0x2bc6a248,0x31ed301d,0x33ea333b,0x333b33ea,0x30c4315f,0x2ed7301d,0x2bc62d64,0x224828b2,0x2bc6315f,0xb15fabc6,0xb3eab388,0xaed7b26d,
  0xa8b2315f,0xb388b2dd,0x301dad64,0x31ed33ea,0xb01d315f,0xa248b3c3,0x30c43388,0xb388b0c4,0xb26d315f,0x333bb01d,0xb3c32d64,0x33fea8b2,
  0xb3c3315f,0x31ed2bc6,0x28b2b388,0xb33b326d,0xb3ea315f,0xad6432dd,0x32ddad64,0x315fb3ea,0xb2dd315f,0xb3fe33c3,0xb26d3388,0xad6430c4,
  0xa8b2a248,0xad64abc6,0xb01daed7,0xb15fb0c4,0x301d2248,0x33fe32dd,0x30c4333b,0xad6428b2,0xb26da248,0xaed7b3c3,0x33c32ed7,0x2248326d,
  0x33c32248,0xb15f301d,0x28b2b33b,0x2ed733ea,0xb3eaa248,0x33882bc6,0xb2ddaed7,0x31ed30c4,0x32dd2248,0xa248b2dd,0xb26d333b,0x3388a8b2,
  0xb0c4a248,0xb33b33c3,0x2bc62ed7,0x33feb26d,0x2bc62248,0x31edb01d,0x33eab33b,0x333bb3ea,0x326d31ed,0x333b32dd,0x33c33388,0x33fe33ea,
  0x33c331ed,0x31ed33c3,0xa8b22d64,0xb33bb0c4,0x33ea31ed,0xad64301d,0xb2ddb388,0x315fa8b2,0x32dd31ed,0xb3feabc6,0x326dad64,0xad64326d,
  0x30c431ed,0xaed7b2dd,0x2bc63388,0xa248b3ea,0x2bc631ed,0x315fb3c3,0xb3ea2d64,0x2ed730c4,0xa8b231ed,0x3388b01d,0x301db388,0xb1ed28b2,
  0xb01d31ed,0x22482bc6,0x30c4ad64,0x3388b26d,0x33ea33fe,0x338833c3,0x32dd333b,0x31ed326d,0xb2ddb3fe,0xa248b01d,0x326d2ed7,0x338833ea,
  0x30c433fe,0xb33babc6,0xabc6b33b,0x33fe30c4,0xabc6b3fe,0x31ed32dd,0xb3eaaed7,0x333ba8b2,0xa8b233fe,0x2d64b3c3,0xb01d333b,0x315fb26d,
  0x301db3fe,0xb3fe301d,0x30c42ed7,0x2d64b3ea,0xb26d33fe,0x2ed72bc6,0x33c3b33b,0xa248b0c4,0x33c3b3fe,0x315fb2dd,0x28b2aed7,0xaed728b2,
  0xb0c4315f,0xaed7301d,0xabc62d64,0xa24828b2,0xabc6315f,0x315fabc6,0x33eab388,0x2ed7b26d,0x28b2315f,0x3388b2dd,0xb01dad64,0xb1ed33ea,
  0x301d315f,0x2248b3c3,0xb0c43388,0x3388b0c4,0x326d315f,0xb33bb01d,0x33c32d64,0xb3fea8b2,0x33c3315f,0xb1ed2bc6,0xa8b2b388,0x333b326d,
  0x33ea315f,0x2d6432dd,0xb2ddad64,0xb15fb3ea,0x32dd315f,0x33fe33c3,0x326d3388,0x2d6430c4,0x28b2a248,0x2d64abc6,0x301daed7,0x315fb0c4,
  0xb01d2248,0xb3fe32dd,0xb0c4333b,0x2d6428b2,0x326da248,0x2ed7b3c3,0xb3c32ed7,0xa248326d,0xb3c32248,0x315f301d,0xa8b2b33b,0xaed733ea,
  0x33eaa248,0xb3882bc6,0x32ddaed7,0xb1ed30c4,0xb2dd2248,0x2248b2dd,0x326d333b,0xb388a8b2,0x30c4a248,0x333b33c3,0xabc62ed7,0xb3feb26d,
  0xabc62248,0xb1edb01d,0xb3eab33b,0xb33bb3ea,0xb26d31ed,0xb33b32dd,0xb3c33388,0xb3fe33ea,0xb3c331ed,0xb1ed33c3,0x28b22d64,0x333bb0c4,
  0xb3ea31ed,0x2d64301d,0x32ddb388,0xb15fa8b2,0xb2dd31ed,0x33feabc6,0xb26dad64,0x2d64326d,0xb0c431ed,0x2ed7b2dd,0xabc63388,0x2248b3ea,
  0xabc631ed,0xb15fb3c3,0x33ea2d64,0xaed730c4,0x28b231ed,0xb388b01d,0xb01db388,0x31ed28b2,0x301d31ed,0xa2482bc6,0xb0c4ad64,0xb388b26d,
  0xb3ea33fe,0xb38833c3,0xb2dd333b,0xb1ed326d,0x32ddb3fe,0x2248b01d,0xb26d2ed7,0xb38833ea,0xb0c433fe,0x333babc6,0x2bc6b33b,0xb3fe30c4,
  0x2bc6b3fe,0xb1ed32dd,0x33eaaed7,0xb33ba8b2,0x28b233fe,0xad64b3c3,0x301d333b,0xb15fb26d,0xb01db3fe,0x33fe301d,0xb0c42ed7,0xad64b3ea,
  0x326d33fe,0xaed72bc6,0xb3c3b33b,0x2248b0c4,0xb3c3b3fe,0xb15fb2dd,0xa8b2aed7,0x2ed728b2,0x29ed29ed,0x29ed29ed,0x29ed29ed,0x29ed29ed,
  0x2bc32a6d,0x2add2bea,0x23c628c4,0xa81da0b2,0x2bc32add,0xa3c6281d,0xabc3aadd,0x23c6a81d,0x29ed2b3b,0xabfea564,0x295fa6d7,0x1a482b88,
  0x25642b88,0xa564ab88,0x25642b88,0xa564ab88,0xa0b22bc3,0x2a6daadd,0xabea23c6,0x28c4281d,0xa8c42bea,0x2a6da0b2,0x28c4abea,0xaa6d20b2,
  0xab3b2bfe,0xa564295f,0x26d79a48,0x2b88a9ed,0x29ed29ed,0x29ed29ed,0x29ed29ed,0x29ed29ed,0xabc3aa6d,0xaaddabea,0xa3c6a8c4,0x281d20b2,
  0x2bc32add,0xa3c6281d,0xabc3aadd,0x23c6a81d,0xa9edab3b,0x2bfe2564,0xa95f26d7,0x9a48ab88,0x25642b88,0xa564ab88,0x25642b88,0xa564ab88,
  0x20b2abc3,0xaa6d2add,0x2beaa3c6,0xa8c4a81d,0xa8c42bea,0x2a6da0b2,0x28c4abea,0xaa6d20b2,0x2b3babfe,0x2564a95f,0xa6d71a48,0xab8829ed,
  0x295f295f,0x295f295f,0x295f295f,0x295f295f,0x23c628c4,0xa81da0b2,0xabc3aa6d,0xaaddabea,0xa3c6281d,0xabc3aadd,0x23c6a81d,0x2bc32add,
  0xa95f26d7,0x9a48ab88,0x29ed2b3b,0xabfea564,0xab882564,0x2b88a564,0xab882564,0x2b88a564,0xabea23c6,0x28c4281d,0x20b2abc3,0xaa6d2add,
  0xaa6d20b2,0xa8c42bea,0x2a6da0b2,0x28c4abea,0xa6d71a48,0xab8829ed,0xab3b2bfe,0xa564295f,0x295f295f,0x295f295f,0x295f295f,0x295f295f,
  0xa3c6a8c4,0x281d20b2,0x2bc32a6d,0x2add2bea,0xa3c6281d,0xabc3aadd,0x23c6a81d,0x2bc32add,0x295fa6d7,0x1a482b88,0xa9edab3b,0x2bfe2564,
  0xab882564,0x2b88a564,0xab882564,0x2b88a564,0x2beaa3c6,0xa8c4a81d,0xa0b22bc3,0x2a6daadd,0xaa6d20b2,0xa8c42bea,0x2a6da0b2,0x28c4abea,
  0x26d79a48,0x2b88a9ed,0x2b3babfe,0x2564a95f,0xabfe2bfe,0xabfe2bfe,0xabfe2bfe,0xabfe2bfe,0xaadd2bea,0xa3c628c4,0x281da0b2,0x2bc3aa6d,
  0xa81d2bc3,0x2adda3c6,0x281dabc3,0xaadd23c6,0x9a482b88,0x29edab3b,0xabfe2564,0x295f26d7,0x26d72b3b,0xa6d7ab3b,0x26d72b3b,0xa6d7ab3b,
  0x2a6d2add,0xabeaa3c6,0x28c4a81d,0x20b22bc3,0x2bea2a6d,0xa0b228c4,0xabeaaa6d,0x20b2a8c4,0x2b8829ed,0x2b3b2bfe,0x2564295f,0xa6d79a48,
  0xabfe2bfe,0xabfe2bfe,0xabfe2bfe,0xabfe2bfe,0x2addabea,0x23c6a8c4,0xa81d20b2,0xabc32a6d,0xa81d2bc3,0x2adda3c6,0x281dabc3,0xaadd23c6,
  0x1a48ab88,0xa9ed2b3b,0x2bfea564,0xa95fa6d7,0x26d72b3b,0xa6d7ab3b,0x26d72b3b,0xa6d7ab3b,0xaa6daadd,0x2bea23c6,0xa8c4281d,0xa0b2abc3,
  0x2bea2a6d,0xa0b228c4,0xabeaaa6d,0x20b2a8c4,0xab88a9ed,0xab3babfe,0xa564a95f,0x26d71a48,0x1a489a48,0x1a489a48,0x1a489a48,0x1a489a48,
  0x281da0b2,0x2bc3aa6d,0x2addabea,0x23c6a8c4,0x2adda3c6,0x281dabc3,0xaadd23c6,0xa81d2bc3,0x2bfea564,0xa95fa6d7,0x9a482b88,0x29edab3b,
  0x2b3ba6d7,0xab3b26d7,0x2b3ba6d7,0xab3b26d7,0x28c4a81d,0x20b22bc3,0xaa6daadd,0x2bea23c6,0x20b2a8c4,0x2bea2a6d,0xa0b228c4,0xabeaaa6d,
  0xa564a95f,0x26d71a48,0x2b8829ed,0x2b3b2bfe,0x1a489a48,0x1a489a48,0x1a489a48,0x1a489a48,0xa81d20b2,0xabc32a6d,0xaadd2bea,0xa3c628c4,
  0x2adda3c6,0x281dabc3,0xaadd23c6,0xa81d2bc3,0xabfe2564,0x295f26d7,0x1a48ab88,0xa9ed2b3b,0x2b3ba6d7,0xab3b26d7,0x2b3ba6d7,0xab3b26d7,
  0xa8c4281d,0xa0b2abc3,0x2a6d2add,0xabeaa3c6,0x20b2a8c4,0x2bea2a6d,0xa0b228c4,0xabeaaa6d,0x2564295f,0xa6d79a48,0xab88a9ed,0xab3babfe,
  0xa95fa95f,0xa95fa95f,0xa95fa95f,0xa95fa95f,0xa3c6a8c4,0x281d20b2,0x2bc32a6d,0x2add2bea,0x23c6a81d,0x2bc32add,0xa3c6281d,0xabc3aadd,
  0x295fa6d7,0x1a482b88,0xa9edab3b,0x2bfe2564,0x2b88a564,0xab882564,0x2b88a564,0xab882564,0x2beaa3c6,0xa8c4a81d,0xa0b22bc3,0x2a6daadd,
  0x2a6da0b2,0x28c4abea,0xaa6d20b2,0xa8c42bea,0x26d79a48,0x2b88a9ed,0x2b3babfe,0x2564a95f,0xa95fa95f,0xa95fa95f,0xa95fa95f,0xa95fa95f,
  0x23c628c4,0xa81da0b2,0xabc3aa6d,0xaaddabea,0x23c6a81d,0x2bc32add,0xa3c6281d,0xabc3aadd,0xa95f26d7,0x9a48ab88,0x29ed2b3b,0xabfea564,
  0x2b88a564,0xab882564,0x2b88a564,0xab882564,0xabea23c6,0x28c4281d,0x20b2abc3,0xaa6d2add,0x2a6da0b2,0x28c4abea,0xaa6d20b2,0xa8c42bea,
  0xa6d71a48,0xab8829ed,0xab3b2bfe,0xa564295f,0x29ed29ed,0x29ed29ed,0x29ed29ed,0x29ed29ed,0x2bc32a6d,0x2add2bea,0x23c628c4,0xa81da0b2,
  0x2bc32add,0xa3c6281d,0xabc3aadd,0x23c6a81d,0x29ed2b3b,0xabfea564,0x295fa6d7,0x1a482b88,0x25642b88,0xa564ab88,0x25642b88,0xa564ab88,
  0xa0b22bc3,0x2a6daadd,0xabea23c6,0x28c4281d,0xa8c42bea,0x2a6da0b2,0x28c4abea,0xaa6d20b2,0xab3b2bfe,0xa564295f,0x26d79a48,0x2b88a9ed,
  0x29ed29ed,0x29ed29ed,0x29ed29ed,0x29ed29ed,0xabc3aa6d,0xaaddabea,0xa3c6a8c4,0x281d20b2,0x2bc32add,0xa3c6281d,0xabc3aadd,0x23c6a81d,
  0xa9edab3b,0x2bfe2564,0xa95f26d7,0x9a48ab88,0x25642b88,0xa564ab88,0x25642b88,0xa564ab88,0x20b2abc3,0xaa6d2add,0x2beaa3c6,0xa8c4a81d,
  0xa8c42bea,0x2a6da0b2,0x28c4abea,0xaa6d20b2,0x2b3babfe,0x2564a95f,0xa6d71a48,0xab8829ed,0x9a481a48,0x9a481a48,0x9a481a48,0x9a481a48,
  0xa81d20b2,0xabc32a6d,0xaadd2bea,0xa3c628c4,0xaadd23c6,0xa81d2bc3,0x2adda3c6,0x281dabc3,0xabfe2564,0x295f26d7,0x1a48ab88,0xa9ed2b3b,
  0xab3b26d7,0x2b3ba6d7,0xab3b26d7,0x2b3ba6d7,0xa8c4281d,0xa0b2abc3,0x2a6d2add,0xabeaa3c6,0xa0b228c4,0xabeaaa6d,0x20b2a8c4,0x2bea2a6d,
  0x2564295f,0xa6d79a48,0xab88a9ed,0xab3babfe,0x9a481a48,0x9a481a48,0x9a481a48,0x9a481a48,0x281da0b2,0x2bc3aa6d,0x2addabea,0x23c6a8c4,
  0xaadd23c6,0xa81d2bc3,0x2adda3c6,0x281dabc3,0x2bfea564,0xa95fa6d7,0x9a482b88,0x29edab3b,0xab3b26d7,0x2b3ba6d7,0xab3b26d7,0x2b3ba6d7,
  0x28c4a81d,0x20b22bc3,0xaa6daadd,0x2bea23c6,0xa0b228c4,0xabeaaa6d,0x20b2a8c4,0x2bea2a6d,0xa564a95f,0x26d71a48,0x2b8829ed,0x2b3b2bfe,
  0xabfe2bfe,0xabfe2bfe,0xabfe2bfe,0xabfe2bfe,0xaadd2bea,0xa3c628c4,0x281da0b2,0x2bc3aa6d,0xa81d2bc3,0x2adda3c6,0x281dabc3,0xaadd23c6,
  0x9a482b88,0x29edab3b,0xabfe2564,0x295f26d7,0x26d72b3b,0xa6d7ab3b,0x26d72b3b,0xa6d7ab3b,0x2a6d2add,0xabeaa3c6,0x28c4a81d,0x20b22bc3,
  0x2bea2a6d,0xa0b228c4,0xabeaaa6d,0x20b2a8c4,0x2b8829ed,0x2b3b2bfe,0x2564295f,0xa6d79a48,0xabfe2bfe,0xabfe2bfe,0xabfe2bfe,0xabfe2bfe,
  0x2addabea,0x23c6a8c4,0xa81d20b2,0xabc32a6d,0xa81d2bc3,0x2adda3c6,0x281dabc3,0xaadd23c6,0x1a48ab88,0xa9ed2b3b,0x2bfea564,0xa95fa6d7,
  0x26d72b3b,0xa6d7ab3b,0x26d72b3b,0xa6d7ab3b,0xaa6daadd,0x2bea23c6,0xa8c4281d,0xa0b2abc3,0x2bea2a6d,0xa0b228c4,0xabeaaa6d,0x20b2a8c4,
  0xab88a9ed,0xab3babfe,0xa564a95f,0x26d71a48,0x3bfb3bff,0x3be53bf2,0x3bbf3bd4,0x3b873ba5,0x3bd03bfb,0x3b013b7c,0x399d3a60,0x378538bc,
  0x35173b52,0xbbc9b7c8,0xb074ba9b,0x3bfe391b,0x319e3b27,0xbbf3b979,0x363cb80a,0x3a2d3bc5,0xba093986,0x3a7eb8f8,0xbae5385f,0x3b3db77a,
  0xbabd393c,0x3bb0b699,0xbc00305b,0x3ba730d7,0xbb2a35c8,0xb8353bb2,0x3a64b1e8,0x3962bbf7,0xba90350b,0xba413bff,0x3602340e,0x3bf6bad8,
  0xac6aa5e4,0xb122af59,0xb402b294,0xb56ab4b7,0xb2deac9c,0xb7bdb5a5,0xb9b3b8d6,0xbb10ba73,0xbb96b676,0xb359bafe,0x3bec3884,0x2a163a29,
  0xbbe0b72c,0x2f27b9d6,0x3b5e3ae8,0xb91633a2,0xb941b9c9,0x38ad3a45,0xb80fbab3,0x36d23b13,0xb850ba0d,0x346f3b4a,0x1fdbbbed,0xb4ab3be8,
  0x3721bb76,0xbace3463,0xb8d13bdd,0x39ebadfb,0x3894bb98,0xb8fd281f,0xbb6a3bbd,0x2e2d3825,0x3b3f3b65,0x3ae83b16,0x3a813ab6,0x3a0d3a49,
  0x3263356a,0xad972b43,0xb5dfb359,0xb8eeb7f3,0xa9b139aa,0xbbedba25,0x3340b889,0x3b983afb,0xbaa2aa16,0xb4cfbb8e,0x3c0038ad,0xb44b38e5,
  0xbb853625,0x3bbdb4c3,0xbbe432ad,0x3bfbaf8b,0xbaacb6d2,0x39243954,0xb65fbace,0x2fbd3bb8,0xb9661648,0xba603bf8,0x383a31cf,0x3b27bbb3,
  0x3219b9eb,0xbb1836f4,0xb9903be5,0x37dd3010,0xb6c6b61a,0xb80ab76f,0xb8a8b85a,0xb93cb8f3,0xbbd7bb87,0xbbf8bbfd,0xbb71bbc9,0xba4dbaf1,
  0xbbfeb9a6,0x305bb91f,0x3bcb3a97,0xb50b37d2,0xb87abbfe,0x3ba13546,0x24523a7e,0xbbb5ba54,0xb576bb63,0x340e3ba3,0xb13bbbd3,0x2c9c3bf2,
  0x386abb3d,0xba2139f8,0x3b57b835,0xbbf13432,0x39e7bc00,0xb8d6adc9,0xbacb3bde,0x372c3457,0x3bdab962,0x3764bb35,0xb9c03122,0xbaf73bef,
  0x398b39cd,0x38fd3946,0x386538b2,0x37853815,0xba85b9c9,0xbb92bb1e,0xbbfebbdd,0xbbc2bbf5,0xb66b3682,0xbb01bb94,0x387fb371,0x3a2d3beb,
  0xbac7bb76,0x3a00ad33,0x36bb3bd4,0xbbeab79b,0xbc0026ad,0x3bf32c38,0xbbd6b109,0x3ba733eb,0x3153bbff,0xb70a3b9e,0x396bba9b,0xbade390c,
  0xb5d4b5bc,0xbbb03b2c,0x32013830,0x3bf6ba67,0x3bccbb52,0x2c06b92e,0xbb83385f,0xb8c73bab,0xb9c5b982,0xba41ba04,0xbab0ba7a,0xbb10bae1,
  0xb8a3b986,0xb52fb74e,0xa94db1e8,0x33d32e91,0xbb54bb4f,0x37bdb523,0x3a9e3bc8,0xb916308d,0x3840b5c8,0x394a3bf9,0xbb42b294,0xb0a6bb0a,
  0x251bbbff,0xaf273bfc,0x327cbbe6,0xb4ab3bc0,0x3be325e4,0xbb2fb4e7,0x39e33884,0xb81aba35,0x3b73bb78,0xb46fb715,0xbbdc3ad1,0x2e2d38cc,
  0x33283676,0x3bfcba19,0x3581bab3,0xba6b3493,0x363136dd,0x34cf3581,0x32c6341a,0x2fbd3153,0xbae1bb65,0xb970ba39,0xb715b889,0xb16cb4f3,
  0xb9a12a7a,0xb924bbfe,0x3a933042,0x37dd3bcc,0x308db9aa,0x3b453b07,0xb94632ad,0xb845bbfa,0xbb68b55e,0x3b1836bb,0xbabab805,0x3a4d38a3,
  0x3bc0b625,0xbbfe2ec3,0x3b9431cf,0xba89b742,0x9cb6b95d,0xbbf8396b,0xb1b63a5c,0x3bb5b840,0x38cc9648,0x3b81bbac,0xac38b85a,0xbbce3933,
  0xbb60bb3a,0xbba1bb83,0xbbd2bbbc,0xbbf1bbe3,0x3815361a,0x39df3907,0x3b2c3a97,0x3be23b9c,0xb9afbbfd,0x3a21294d,0x388e3bee,0xbaf7b328,
  0x3beb39a6,0xb6af37a6,0xba04bbd3,0x3ac42d00,0x360ebb89,0xb7643b42,0x3855baeb,0xb8ee3a85,0x33eb3b63,0x28e8bbf5,0xb5233bde,0x389ebb21,
  0x3c00b9f0,0x2d97b9e3,0xbbdf38db,0xb44b3ac7,0xba673c00,0x358d3487,0x3bfcbab6,0x330fba15,0x3b7a3bf1,0x394a3a93,0x33893764,0xb3d39cb6,
  0x3afb3be2,0x35eb3946,0xb4c328e8,0xbaa9b8cc,0x27763af7,0xbb2fbaba,0x3a76ad97,0x30a63b60,0xaf8b3ac4,0xb994bb94,0x3bf8358d,0xb8743815,
  0xbb4c38ee,0x3bfcb1b6,0xbad5b4cf,0x381a39af,0xbbb3389e,0x3b592c38,0xb76fb970,0xb24b3beb,0xb9d2344b,0xbb923bd2,0xb0f03924,0x3a6bb60e,
  0xb8f3330f,0xbc003b2c,0xb91f3b45,0x323233eb,0xb5b1afbd,0xba00b88e,0xbbc6bb18,0xbbc2bc00,0xb7d2b16c,0xbb6fba04,0xbba3bbfe,0xb86fba67,
  0xbbffb7dd,0x370ab855,0x38b73bf8,0xbbeab631,0xbbf2b845,0x39bcb523,0x2dc93b81,0xbaa5bae1,0xb68dba4d,0xac063bdf,0x382abba1,0xbade39a1,
  0xb457ba89,0xb6543bfc,0x3b16b9df,0xbbd8308d,0x397dbbb5,0xb52fb2c6,0xbbe73a21,0xb8c73b68,0x3a49bbce,0x2311b715,0xba2536af,0xbbd93bc0,
  0xb958b785,0xbb81ba9e,0xbbefbbf3,0xba89bb73,0xbbf7bbc2,0xb9b8bb42,0xaf59b70a,0x384a3328,0xbb8bba2d,0x39dfb27c,0x34263bb0,0xbbceb98b,
  0xb4b7bbea,0x3b6c39e3,0xbafe2c06,0x3185ba85,0xaadebba7,0xb6af3bdc,0x3a58ba41,0xbbe2366b,0x3a29bade,0xbc003581,0x3a45352f,0xb2f7bac7,
  0x3b37bbf6,0x28e8b865,0xbaee37bd,0xbac43c00,0x3b13b8c7,0x3b5cbbfe,0x3463b94a,0xb8993153,0xb9f4bb10,0xb58db87f,0x3029af27,0x389e35d4,
  0x2dfbb3d3,0x399936bb,0x3bf23b2f,0x3ac13bcc,0x3552b916,0x39703bd6,0xbbbab46f,0x330fb9c5,0x3ba530a6,0xb5f7396b,0xb7c8bbfc,0x3be138a3,
  0x3bfdb4ab,0xbb45b201,0x38e038fd,0xb16cbb54,0x391b381a,0xa17fbb83,0xb8f83b92,0x3bcfb840,0x36e82e2d,0x3bfebab0,0x37febb01,0xb845251b,
  0xb77a3a6b,0x3648294d,0x3bb2ba00,0x3a8cbbe3,0xb742b93c,0x2311b340,0x37a6340e,0x3aa93966,0x3b963a4d,0x3b7f3c00,0x380f3a21,0xb0be3219,
  0x3933b50b,0x35eb3be4,0xbbf5b8d6,0x3874b6c6,0x39413bb5,0xbbffb65f,0x38d1b764,0x33ba3bd7,0x3b9c2c9c,0xb994b83a,0x34873ae8,0x324bbbfe,
  0xb7213bf1,0x3b47b990,0xbbbf2d97,0x38c1387a,0x2d00372c,0x3b59b8a8,0x3a39bbed,0xb232b576,0xbbfb3af7,0xb9743b71,0x307434cf,0x3adbb86a,
  0x3b213a0d,0x3c003bcb,0x3b073bbd,0x386f39e7,0x351738ee,0xb599a452,0xbae5b924,0xbbe9bbda,0x3a153b98,0xbb6fb13b,0x2ec3ba60,0x3aa53b3f,
  0xba09344b,0xa884bb57,0x3a643b18,0xbbc3b263,0xb4f33bfb,0x39bcbacb,0xbbac380a,0x3bd8a9b1,0xbb2aafbd,0x36a439c0,0x3402bbf8,0xba6f3aa2,
  0xbbfa3b27,0xb6543a81,0x3907b05b,0x3bd9bb85,0x2c6ab7dd,0xb9da35df,0xbbec3ba1,0xb8203aac,0x3bf53b87,0x3b6c3bec,0x392e3a7e,0x32f73721,
  0xb9e7b785,0xbbfcbb5e,0xba81bbb0,0xb43eb894,0x379b3bfe,0xbc00b80f,0x374eb835,0x38993bfb,0xbb3fba2d,0x3b329fdb,0xb3403a41,0xb8eabbd0,
  0xb90c3b3d,0x3b5cb8d1,0xbbf93122,0x3ac13517,0x29b1bba7,0xb94f3b6a,0x3be4b7bd,0xbaf4b19e,0xbbab3962,0xb9993bbf,0x34e73359,0x3be1ba09,
  0x3b85bbf6,0x353ab99d,0xb83a2f27,0xbbf03abd,0x2e91356a,0xb5f7b074,0xba19b8ad,0xbbcfbb2a,0xb966bb10,0xaba7b63c,0x38a8346f,0x3bb73a90,
  0xbb0aaa16,0xa17fbae5,0x3b1e3ace,0xba8c2c6a,0x36c6b916,0x36ff3c00,0xbbcbb8fd,0x3a50b2de,0xba35b6d2,0x36483a64,0x2d33bbe5,0xb84a3b96,
  0x3bfeb4ab,0xb9fcb602,0x313b3b01,0x37e8bbe0,0x3493b9eb,0xb9b83402,0xbb9e3bc9,0xb1853941,0x35762e2d,0x3b90b9b3,0x3acbbbf3,0x2fefb850,
  0x3a543bcf,0x2884374e,0xb9f8b648,0xbbe9bbab,0x398b3bb7,0xb4db3340,0xbbdcb9fc,0xb911bb85,0xb4323a8c,0xb6a4bbf9,0x3b3539b8,0xbbc3ae91,
  0xb66b3a50,0xad65bbe4,0x38653b90,0xbb0db966,0xbbef384a,0x39da34e7,0x2b43bb6c,0xba6f3b0a,0xbc0037e8,0x3759383a,0x387fbbfc,0xbbf636c6,
  0xb7f33185,0xbb7f3a19,0xbb8e3c00,0xb8203a35,0xb5d42fef,0xba1d38a8,0xbbd63b32,0xbba93bfe,0xb8e5b2f7,0xbbffbb1e,0xb954bb5c,0x30beb493,
  0xb9c5b43e,0xbb9fbbcb,0xb201b94f,0x3a313576,0xbbb8b899,0x3b47ad33,0xb6f43999,0xb3babbf5,0xbb54b8ea,0x3bf9313b,0xbab0353a,0x3790b9e7,
  0xb010bac1,0xb9743b9e,0x3bfdb5f7,0xb8c1b79b,0x251bbaf4,0xbb1b3acb,0x3a9e2ba7,0x2e5fbb3f,0x3af1bbe1,0x3599b92e,0xb546a17f,0xbadb390c,
  0x3b73bbf0,0x3929ba81,0x327cb6ff,0xb49f29b1,0xb825baa9,0x353aaec3,0x3b7c3994,0x3af43bfa,0x360eb0be,0x3bf43a64,0x388e3b47,0xb7372c6a,
  0x38bcb874,0x2ba73bac,0xb979bb59,0x3bf03742,0x3c0033ba,0xbb043402,0x3855b974,0xacce3b96,0x3bc5b24b,0xb6ffb907,0xb6993c00,0x3bb7b933,
  0x363138c1,0x3902bbec,0xbbdf3599,0x34ff3941,0x30d73232,0x39fcb7a6,0x3bffbb6f,0x3a50bb9c,0xb9a13adb,0xb47b380f,0x32c62884,0x3937b721,
  0x3ad8386f,0x3b903bf5,0x35a539bc,0xb7e8ad00,0x3b683be9,0x2ef538d1,0xba93b6a4,0xbb24bbfb,0x3a733aa5,0xbbfcb487,0x39d6b654,0xafef3b21,
  0x1cb63bc3,0xb7b2bbbf,0x3aba39da,0xbbfab517,0xb3a23bd8,0x3b32ba39,0xbb4a2311,0x343e3a15,0xbb603a6f,0x3a3d3074,0x31b6bb7f,0xbb9a3a09,
  0xbbe83bd9,0xb94f3b07,0xa81f35eb,0x38eab4f3,0xb9af3820,0xbbae3ae5,0xbbd23bff,0xba113b2a,0x319e389e,0xb929b426,0xbc00bb45,0xb911bb37,
  0xbbffbac1,0xb805bafe,0x382a217f,0x3bfd3b13,0xbabd330f,0x34dbba58,0x36023bfe,0xbb0db9f4,0xb68dbbe1,0x3a5c3a45,0xbbe7b648,0x3b89adfb,
  0xba90b16c,0x2d653aee,0x39b3bb81,0xbbf63552,0x397dbbcf,0xbbbc3463,0x338939b8,0x39f0bba5,0x32deb845,0xb7593029,0xbb5e39df,0xbba93bfd,
  0x3b7aba8c,0x3beebbf2,0x3a76bb6c,0x36ddb91b,0xbbe0ba89,0xba1dbbba,0x1fdbb6af,0x3a3136e8,0xa776b84a,0x3aeb37c8,0x3ad53c00,0xaa7a377a,
  0xb850bbce,0x3b9f38e0,0xbb6a28e8,0x3790b958,0x3b4cb185,0xb8db38f8,0x30f0bb5c,0x355e3bf7,0x3894bbe2,0xbbf937fe,0x399d358d,0x2e5fbb8b,
  0x39d232f7,0x341abbb2,0xbbc63999,0x395d34b7,0x3bd0bac4,0x3b1bbbef,0x363cb970,0xb49faade,0xb5b13899,0x30422f59,0x38b7b5f7,0x3b3aba29,
  0x3219b3d3,0x3b0438b7,0x3b713bfc,0x34ff397d,0x36e83aa9,0xb8b2adc9,0xbbefbb59,0xb5bcba49,0x3bd730a6,0xb902382a,0xa452bb92,0x39373b7a,
  0xb9583874,0x3371bb16,0x34263c00,0xb982bafb,0x387a381a,0x347bbbe7,0xbb573a00,0x3b242776,0xbb8b324b,0x31093a25,0x3a58bb6f,0xbb4f2f8b,
  0xb86a3a6b,0x2ef53389,0x39c0b70a,0x3bfabb4c,0xaadeb232,0xb83034c3,0xbaee39bc,0xbbff3bb3,0x3bda3bc2,0x37b23a76,0xb5df2c06,0xbb9ab9d2,
  0xbb37b86f,0xba7abbf8,0x3029b654,0x3b7838f3,0x32633bea,0xba3dbad5,0x3c00352f,0xba1135b1,0xb9f4baa5,0x3bc8376f,0xbbba2311,0x39cdb7d2,
  0xbaa23ade,0x3baeb0f0,0xb65fb94a,0xb7373bff,0x3552bbd8,0xbbe6391f,0x38e035eb,0x3682bbf2,0xbaac38c7,0xbbf43bc6,0xb9903b2f,0xacce368d,
  0x3bfdbbd9,0x3ad1bba3,0x37feb994,0x26adb457,0x38a33b9a,0xb8dba452,0xbb83bbae,0x2a7ab86a,0x37423b78,0xbab6b426,0xb907bbe6,0x39aa2ade,
  0xb8403a11,0x341abb57,0x294d3bf4,0xb55ebbda,0xb93339cd,0x3889ba58,0xb7a63ad1,0x3625bb37,0xbbe33737,0x304239c0,0x3b42bb04,0xb95db263,
  0xbb9c3682,0xb2ad3aee,0x3bf5b8b2,0x1648b9f4,0xb3282cce,0xb80535df,0xb9e33902,0xbb3a3aa2,0xad0026ad,0xb1cf3029,0xb4873371,0xb61a3552,
  0xba85b4ff,0xba5cbc00,0x3581b47b,0x3bfd3aac,0xbb21b5bc,0xb85abbba,0x3a393109,0x39a63bfd,0xbac7b937,0x3bbc365f,0xbbfeaef5,0x3b89b219,
  0xba15b982,0x3a9738e0,0xbb07b830,0x3b6336e8,0x3153bb24,0xbbee3990,0x36bb37b2,0x39f0bbd7,0x34f3bb4f,0xbbd337fe,0xaec33a7a,0x3c00b958,
  0x3bccbbfa,0x3aebbb71,0x396bba3d,0x36ddb87a,0x3bfabbff,0x3bdebbef,0x3bacbbc8,0x3b65bb8b,0x3bc03911,0x38303b6a,0xb946ad65,0xbb4fbbd0,
  0x3a353bfd,0xb85f30f0,0xbb1ebbbc,0x35c8b5b1,0x38cc3b0d,0xba7ab99d,0x3b943759,0xbbffb19e,0xb4933b89,0x31e8bbc6,0xad333bee,0xa5e4bbff,
  0xb8153bf6,0x3bc8b63c,0xac38ba1d,0xbb783abd,0xbbf539f0,0x329438b7,0x3b9ebaeb,0xb676b68d,0xbbeb3ba9,0xbbe63c00,0xbb2c3b9f,0xb9cd3a90,
  0xb79b36dd,0xb884382a,0xb92e38db,0xb9c9397d,0x33eb3a31,0xbad1b602,0xba04bbf9,0x3682b2de,0xb90c2a7a,0xbab3bbe7,0x374eb41a,0x3b763b7a,
  0xba673790,0x38b2b9b3,0xb5233b1b,0x26adbbe0,0xbbabb55e,0x3bdd3389,0xbbf9b042,0x3bff2776,0xbae12e5f,0xb3713b5e,0x3bfcb929,0xb5bcb850,
  0xae91b95d,0xbbd43a76,0x34e73805,0x3b52bb4c,0x308db49f,0xb1091fdb,0xb71534db,0xb9823894,0x3b0abb3a,0x3a9bbad5,0x3a19ba5c,0x3986b9d2,
  0x2f8bb7e8,0x3bde3979,0x376f3b32,0xb9aab0d7,0x3bb83b24,0xb1223855,0xbbfdba3d,0xaa16b9a1,0x3bb3afef,0xbab63699,0x391fb94f,0xb6253ad8,
  0x30103bfa,0xb359bbdf,0x35463bae,0xb6d2bb68,0x38f3343e,0x3889bbff,0xbba3353a,0x96483a73,0xbaf13b9a,0x38ad32c6,0x39f8bbf4,0xb9eb9cb6,
  0xb7d238ea,0xb2ad35a5,0x2dc92ba7,0x361ab3a2,0xba543a11,0xbace3a93,0xbb353b04,0xbb873b60,0x3bf23af4,0x31cf39d6,0xbb16b6ff,0xb9a6bbe8,
  0xb4323737,0xbbe5baba,0x2b43b902,0x3bfe39af,0x34573bf0,0xb85abb4a,0x3a2539fc,0xbb63b825,0xbbef2cce,0x3bc9b1b6,0xbb8e347b,0x3b3db60e,
  0xba493bb7,0x3a97a81f,0x34c3bb90,0xbc0038bc,0xb7f3b4ff,0xba7e3bd2,0x39542ef5,0x3962bc00,0xbafb3a50,0xbbd33b7c,0xbbf83bfc,0xbb653bc5,
  0x38e5b937,0x3835b88e,0x36f4b7b2,0x356ab631,0xbb13bbe9,0x31e8b6f4,0x3bf239da,0x36763af1,0x3be83911,0x340e3ab0,0xbb7cb759,0xb72cbb73,
  0x2dfbbbc3,0x32943bfd,0xb7c8bb7f,0x39c93a54,0x38253b0d,0xb8d6ba9e,0x39793a1d,0xba0db98b,0x3ba5ba6f,0xb884b546,0xb8f83bff,0x3b76b432,
  0xb8bc3bf6,0x3ae8b27c,0x3699bb9f,0xbb98366b,0x391bb820,0x3ab3b9f8,0x3bb2bb47,0x3bffbbef,0xbbc53ba9,0xbbed3bdc,0xbbff3bf9,0xbbfb3c00,
  0x377ab0be,0x3bdd3b35,0x2f593974,0xbb52b7f3,0x30d73a31,0xbbbdb865,0xb5a5bb1b,0x3b2735d4,0x3bf733ba,0xbbd42b43,0x3afeb599,0xb98638e5,
  0xbad83790,0x3a60b87f,0xb9d63929,0x393cb9c5,0x34b738c1,0x3a9bbb8e,0xba45a884,0xb5c83bb8,0xba732e5f,0xb80a3bd6,0x3b4ab4db,0x350bbb54,
  0xba293adb,0xb85f3954,0xb46336a4,0x25e43010,0x33a2b49f,0x305bb201,0x281fad65,0xac9c251b,0x3f803f80,0x3f803f80,0x3f803f80,0x3f803f80,
  0x3f803f80,0x3f803f80,0x3f803f80,0x3f803f80,0x3f803f80,0x3f803f80,0x3f803f80,0x3f803f80,0x3f803f80,0x3f803f80,0x3f803f80,0x3f803f80,
  0x3f803f80,0x3f803f80,0x3f803f80,0x3f803f80,0x3f803f80,0x3f803f80,0x3f803f80,0x3f803f80,0x3f803f80,0x3f803f80,0x3f803f80,0x3f803f80,
  0x3f803f80,0x3f803f80,0x3f803f80,0x3f803f80,0x3f803f80,0x3f803f80,0x3f803f80,0x3f803f80,0x3f803f80,0x3f803f80,0x3f803f80,0x3f803f80,
  0x3f803f80,0x3f803f80,0x3f803f80,0x3f803f80,0x3f803f80,0x3f803f80,0x3f803f80,0x3f803f80,0x3f803f80,0x3f803f80,0x3f803f80,0x3f803f80,
  0x3f803f80,0x3f803f80,0x3f803f80,0x3f803f80,0x3f803f80,0x3f803f80,0x3f803f80,0x3f803f80,0x3f803f80,0x3f803f80,0x3f803f80,0x3f803f80,
  0x3f803f80,0x3f803f80,0x3f803f80,0x3f803f80,0x3f803f80,0x3f803f80,0x3f803f80,0x3f803f80,0x3f803f80,0x3f803f80,0x3f803f80,0x3f803f80,
  0x3f803f80,0x3f803f80,0x3f803f80,0x3f803f80,0x3f803f80,0x3f803f80,0x3f803f80,0x3f803f80,0x3f803f80,0x3f803f80,0x3f803f80,0x3f803f80,
  0x3f803f80,0x3f803f80,0x3f803f80,0x3f803f80,0x3f803f80,0x3f803f80,0x3f803f80,0x3f803f80,0x3f803f80,0x3f803f80,0x3f803f80,0x3f803f80,
  0x3f803f80,0x3f803f80,0x3f803f80,0x3f803f80,0x3f803f80,0x3f803f80,0x3f803f80,0x3f803f80,0x3f803f80,0x3f803f80,0x3f803f80,0x3f803f80,
  0x3f803f80,0x3f803f80,0x3f803f80,0x3f803f80,0x3f803f80,0x3f803f80,0x3f803f80,0x3f803f80,0x3f803f80,0x3f803f80,0x3f803f80,0x3f803f80,
  0x3f803f80,0x3f803f80,0x3f803f80,0x3f803f80,0x3f803f80,0x3f803f80,0x3f803f80,0x3f803f80,0x3f803f80,0x3f803f80,0x3f803f80,0x3f803f80,
  0x3f803f80,0x3f803f80,0x3f803f80,0x3f803f80,0x3f803f80,0x3f803f80,0x3f803f80,0x3f803f80,0x3f803f80,0x3f803f80,0x3f803f80,0x3f803f80,
  0x3f803f80,0x3f803f80,0x3f803f80,0x3f803f80,0x3f803f80,0x3f803f80,0x3f803f80,0x3f803f80,0x3f803f80,0x3f803f80,0x3f803f80,0x3f803f80,
  0x3f803f80,0x3f803f80,0x3f803f80,0x3f803f80,0x3f803f80,0x3f803f80,0x3f803f80,0x3f803f80,0x3f803f80,0x3f803f80,0x3f803f80,0x3f803f80,
  0x3f803f80,0x3f803f80,0x3f803f80,0x3f803f80,0x3f803f80,0x3f803f80,0x3f803f80,0x3f803f80,0x3f803f80,0x3f803f80,0x3f803f80,0x3f803f80,
  0x3f803f80,0x3f803f80,0x3f803f80,0x3f803f80,0x3f803f80,0x3f803f80,0x3f803f80,0x3f803f80,0x3f803f80,0x3f803f80,0x3f803f80,0x3f803f80,
  0x3f803f80,0x3f803f80,0x3f803f80,0x3f803f80,0x3f803f80,0x3f803f80,0x3f803f80,0x3f803f80,0x3f803f80,0x3f803f80,0x3f803f80,0x3f803f80,
  0x3f803f80,0x3f803f80,0x3f803f80,0x3f803f80,0x3f803f80,0x3f803f80,0x3f803f80,0x3f803f80,0x3f803f80,0x3f803f80,0x3f803f80,0x3f803f80,
  0x3f803f80,0x3f803f80,0x3f803f80,0x3f803f80,0x3f803f80,0x3f803f80,0x3f803f80,0x3f803f80,0x3f803f80,0x3f803f80,0x3f803f80,0x3f803f80,
  0x3f803f80,0x3f803f80,0x3f803f80,0x3f803f80,0x3f803f80,0x3f803f80,0x3f803f80,0x3f803f80,0x3f803f80,0x3f803f80,0x3f803f80,0x3f803f80,
  0x3f803f80,0x3f803f80,0x3f803f80,0x3f803f80,0x3f803f80,0x3f803f80,0x3f803f80,0x3f803f80,0x3f803f80,0x3f803f80,0x3f803f80,0x3f803f80,
  0x3f803f80,0x3f803f80,0x3f803f80,0x3f803f80,0x3f803f80,0x3f803f80,0x3f803f80,0x3f803f80,0x3f803f80,0x3f803f80,0x3f803f80,0x3f803f80,
  0x3f803f80,0x3f803f80,0x3f803f80,0x3f803f80,0x3f803f80,0x3f803f80,0x3f803f80,0x3f803f80,0x3f803f80,0x3f803f80,0x3f803f80,0x3f803f80,
  0x3f803f80,0x3f803f80,0x3f803f80,0x3f803f80,0x3f803f80,0x3f803f80,0x3f803f80,0x3f803f80,0x3f803f80,0x3f803f80,0x3f803f80,0x3f803f80,
  0x3f803f80,0x3f803f80,0x3f803f80,0x3f803f80,0x3f803f80,0x3f803f80,0x3f803f80,0x3f803f80,0x3f803f80,0x3f803f80,0x3f803f80,0x3f803f80,
  0x3f803f80,0x3f803f80,0x3f803f80,0x3f803f80,0x3f803f80,0x3f803f80,0x3f803f80,0x3f803f80,0x3f803f80,0x3f803f80,0x3f803f80,0x3f803f80,
  0x3f803f80,0x3f803f80,0x3f803f80,0x3f803f80,0x3f803f80,0x3f803f80,0x3f803f80,0x3f803f80,0x3f803f80,0x3f803f80,0x3f803f80,0x3f803f80,
  0x3f803f80,0x3f803f80,0x3f803f80,0x3f803f80,0x3f803f80,0x3f803f80,0x3f803f80,0x3f803f80,0x3f803f80,0x3f803f80,0x3f803f80,0x3f803f80,
  0x3f803f80,0x3f803f80,0x3f803f80,0x3f803f80,0x3f803f80,0x3f803f80,0x3f803f80,0x3f803f80,0x3f803f80,0x3f803f80,0x3f803f80,0x3f803f80,
  0x3f803f80,0x3f803f80,0x3f803f80,0x3f803f80,0x3f803f80,0x3f803f80,0x3f803f80,0x3f803f80,0x3f803f80,0x3f803f80,0x3f803f80,0x3f803f80,
  0x3f803f80,0x3f803f80,0x3f803f80,0x3f803f80,0x3f803f80,0x3f803f80,0x3f803f80,0x3f803f80,0x3f803f80,0x3f803f80,0x3f803f80,0x3f803f80,
  0x3f803f80,0x3f803f80,0x3f803f80,0x3f803f80,0x3f803f80,0x3f803f80,0x3f803f80,0x3f803f80,0x3f803f80,0x3f803f80,0x3f803f80,0x3f803f80,
  0x3f803f80,0x3f803f80,0x3f803f80,0x3f803f80,0x3f803f80,0x3f803f80,0x3f803f80,0x3f803f80,0x3f803f80,0x3f803f80,0x3f803f80,0x3f803f80,
  0x3f803f80,0x3f803f80,0x3f803f80,0x3f803f80,0x3f803f80,0x3f803f80,0x3f803f80,0x3f803f80,0x3f803f80,0x3f803f80,0x3f803f80,0x3f803f80,
  0x3f803f80,0x3f803f80,0x3f803f80,0x3f803f80,0x3f803f80,0x3f803f80,0x3f803f80,0x3f803f80,0x3f803f80,0x3f803f80,0x3f803f80,0x3f803f80,
  0x3f803f80,0x3f803f80,0x3f803f80,0x3f803f80,0x3f803f80,0x3f803f80,0x3f803f80,0x3f803f80,0x3f803f80,0x3f803f80,0x3f803f80,0x3f803f80,
  0x3f803f80,0x3f803f80,0x3f803f80,0x3f803f80,0x3f803f80,0x3f803f80,0x3f803f80,0x3f803f80,0x3f803f80,0x3f803f80,0x3f803f80,0x3f803f80,
  0x3f803f80,0x3f803f80,0x3f803f80,0x3f803f80,0x3f803f80,0x3f803f80,0x3f803f80,0x3f803f80,0x3f803f80,0x3f803f80,0x3f803f80,0x3f803f80,
  0x3f803f80,0x3f803f80,0x3f803f80,0x3f803f80,0x3f803f80,0x3f803f80,0x3f803f80,0x3f803f80,0x3f803f80,0x3f803f80,0x3f803f80,0x3f803f80,
  0x3f803f80,0x3f803f80,0x3f803f80,0x3f803f80,0x3f803f80,0x3f803f80,0x3f803f80,0x3f803f80,0x3f803f80,0x3f803f80,0x3f803f80,0x3f803f80,
  0x3f803f80,0x3f803f80,0x3f803f80,0x3f803f80,0x3f803f80,0x3f803f80,0x3f803f80,0x3f803f80,0x3f803f80,0x3f803f80,0x3f803f80,0x3f803f80,
  0x3f803f80,0x3f803f80,0x3f803f80,0x3f803f80,0x3f803f80,0x3f803f80,0x3f803f80,0x3f803f80,0x3f803f80,0x3f803f80,0x3f803f80,0x3f803f80,
  0x3f803f80,0x3f803f80,0x3f803f80,0x3f803f80,
};

__device__ __align__(128) float    g_part[16][8][2176];
__device__ __align__(128) float    g_kv[16][2176];
__device__ __align__(128) uint4    g_o[16 * 16 * 1024];
__device__ __align__(128) unsigned g_ocnt[2 * 16 * 32];
__device__ unsigned g_epoch[128];
#define GSTAMP(role, i) do {} while (0)
#define STAMP(role, i) do {} while (0)
#define PDUMP(role) do {} while (0)
#define PROF_SMEM 0

constexpr int STAGE_BYTES = 57344;
constexpr int OFF_H = 4 * 16384, OFF_VP = 9 * 16384, OFF_SPARE = 10 * 16384;
constexpr int OFF_XT = 172032, XT_STRIDE = 4112;
constexpr int OFF_BAR = 204928, OFF_EPOCH = OFF_BAR + 640, OFF_EX = OFF_BAR + 656, OFF_D = OFF_BAR + 672, OFF_SCALE = OFF_BAR + 704;
constexpr int OFF_F2F = 205824, OFF_F2I = 207872, OFF_F4 = 209920, OFF_ONES = 214016, OFF_KVB = 214016;
constexpr int OFF_STG = 219136, STG_STRIDE = 4352, SMEM_TOTAL = 232192 + PROF_SMEM;
enum { B_FULL1 = 0, B_EMPTY1 = 3, B_Q = 6, B_ODONE1 = 7, B_O1RDY = 8, B_H = 9, B_XRAW = 10, B_XT = 11, B_KV = 12, B_Y = 13,  B_AFREE = 15,
       B_STG = 18, B_ODONE = 24, B_XFREE = 25, B_FULL2 = 33, B_CONS2 = 49, B_SFREE = 14, B_PKRDY = 62, B_PKFREE = 64, B_H2 = 65, B_COUNT = 66 };
__host__ __device__ constexpr int bar_count(int i) {
  return i < B_EMPTY1 ? 1 : i < B_Q ? 4 : i == B_XT ? 4 : i == B_H ? 4 : i == B_SFREE ? 2 : i >= B_PKFREE ? 4 : i >= B_PKRDY ? 8 : i == B_KV ? 2 : i == B_Y ? 9
       : (i >= B_AFREE && i < B_STG) ? 16 : (i == B_ODONE || i == B_ODONE1) ? 8 : (i >= B_XFREE && i < B_FULL2) ? 4
       : i >= B_CONS2 ? 4 : (i >= B_FULL2 && i < B_FULL2 + 7) ? 2 : 1;
}
__host__ __device__ constexpr uint64_t bar_counts(int r) {
  uint64_t v = 0;
  for (int w = 0; w < 11; w++) v |= (uint64_t)(bar_count(1 + 11 * r + w) - 1) << (4 * w);
  return v;
}
constexpr uint64_t SLOT_A = 0x9645296452964594ull;
constexpr uint64_t SLOT_B = 0x7103871038710326ull;
constexpr uint32_t SW128 = 64 | (1u << 30);
constexpr int SPIN_LIMIT = 1 << 22;
#define PKV CU_TENSOR_MAP_L2_PROMOTION_L2_128B
#define BPRE B_KV
#define PFD 3
#define PD1 0
#define PD2 100
#define E1C 2
#define OSP 4
#define QPF 6
#define TSPLIT 1
#define OC0 2
#define OC1 2
#define BSPL 4
#define BPACE 250
#define NPOS 0
#define O1POS 1
#define HL1 4
#define OCH 3
#define O1D 3
#define QPOS 2
#define HOLD2 13
#define A0COL 0
#define KPOS 1
#define CWAIT 0
#define HSPL 12
#define BEARLY 3
#define BLATE B_KV
#define G2LA 0
#define G2W0 0
#define G2S 2
#define HSTART 1500
#define PACE 800
#define OC 1

__device__ __forceinline__ uint32_t smem_u32(const void* p) { return (uint32_t)__cvta_generic_to_shared(p); }
__device__ __forceinline__ void wg_fence() { asm volatile("wgmma.fence.sync.aligned;" ::: "memory"); }
__device__ __forceinline__ void wg_commit() { asm volatile("wgmma.commit_group.sync.aligned;" ::: "memory"); }
template <int N> __device__ __forceinline__ void wg_wait() { asm volatile("wgmma.wait_group.sync.aligned %0;" ::"n"(N) : "memory"); }
template <int N> __device__ __forceinline__ void keep(float (&d)[N]) {
#pragma unroll
  for (int i = 0; i < N; i++) asm volatile("" : "+f"(d[i])::"memory");
}
__device__ __forceinline__ uint64_t mkdesc(uint32_t addr, uint32_t lbo, uint32_t sbo, uint32_t swz) {
  uint32_t lo = ((addr & 0x3FFFF) >> 4) | ((lbo >> 4) << 16), hi = (sbo >> 4) | (swz << 30);
  return ((uint64_t)hi << 32) | lo;
}
__device__ __forceinline__ void mbar_init(uint32_t bar, int cnt) { asm volatile("mbarrier.init.shared::cta.b64 [%0], %1;" ::"r"(bar), "r"(cnt)); }
__device__ __forceinline__ void mbar_expect(uint32_t bar, int bytes) { asm volatile("mbarrier.arrive.expect_tx.shared::cta.b64 _, [%0], %1;" ::"r"(bar), "r"(bytes) : "memory"); }
__device__ __forceinline__ void mbar_arrive(uint32_t bar) { asm volatile("mbarrier.arrive.shared::cta.b64 _, [%0];" ::"r"(bar) : "memory"); }
__device__ __forceinline__ void mbar_arrive_cl(uint32_t bar, uint32_t cta) {
  asm volatile("{\n.reg .b32 r;\nmapa.shared::cluster.u32 r, %0, %1;\nmbarrier.arrive.shared::cluster.b64 _, [r];\n}\n" ::"r"(bar), "r"(cta) : "memory");
}
__device__ __forceinline__ void mbar_wait(uint32_t bar, uint32_t parity) {
  asm volatile("{\n.reg .pred p;\n.reg .u32 n;\nmov.u32 n, 0;\n"
               "W_%=:\nmbarrier.try_wait.parity.shared::cta.b64 p, [%0], %1;\n@p bra D_%=;\n"
               "add.u32 n, n, 1;\nsetp.lt.u32 p, n, %2;\n@p bra W_%=;\ntrap;\nD_%=:\n}\n" ::"r"(bar), "r"(parity), "n"(SPIN_LIMIT) : "memory");
}
__device__ __forceinline__ void fence_async() { asm volatile("fence.proxy.async.shared::cta;" ::: "memory"); }
__device__ __forceinline__ void bar_sync(int id) { asm volatile("bar.sync %0, 128;" ::"r"(id) : "memory"); }
__device__ __forceinline__ void tma2d(uint32_t dst, const CUtensorMap* m, int c0, int c1, uint32_t bar) {
  asm volatile("cp.async.bulk.tensor.2d.shared::cluster.global.mbarrier::complete_tx::bytes [%0], [%1, {%3, %4}], [%2];"
               ::"r"(dst), "l"(m), "r"(bar), "r"(c0), "r"(c1) : "memory");
}
__device__ __forceinline__ void tma2d_mc(uint32_t dst, const CUtensorMap* m, int c0, int c1, uint32_t bar) {
  asm volatile("cp.async.bulk.tensor.2d.shared::cluster.global.mbarrier::complete_tx::bytes.multicast::cluster [%0], [%1, {%3, %4}], [%2], %5;"
               ::"r"(dst), "l"(m), "r"(bar), "r"(c0), "r"(c1), "h"((uint16_t)3) : "memory");
}
__device__ __forceinline__ void tma3d(uint32_t dst, const CUtensorMap* m, int c0, int c1, int c2, uint32_t bar) {
  asm volatile("cp.async.bulk.tensor.3d.shared::cluster.global.mbarrier::complete_tx::bytes [%0], [%1, {%3, %4, %5}], [%2];"
               ::"r"(dst), "l"(m), "r"(bar), "r"(c0), "r"(c1), "r"(c2) : "memory");
}
__device__ __forceinline__ void tma4d(uint32_t dst, const CUtensorMap* m, int c0, int c1, int c2, int c3, uint32_t bar) {
  asm volatile("cp.async.bulk.tensor.4d.shared::cluster.global.mbarrier::complete_tx::bytes [%0], [%1, {%3, %4, %5, %6}], [%2];"
               ::"r"(dst), "l"(m), "r"(bar), "r"(c0), "r"(c1), "r"(c2), "r"(c3) : "memory");
}
__device__ __forceinline__ void bulk_ld(uint32_t dst, const void* src, int bytes, uint32_t bar) {
  asm volatile("cp.async.bulk.shared::cluster.global.mbarrier::complete_tx::bytes [%0], [%1], %2, [%3];" ::"r"(dst), "l"(src), "r"(bytes), "r"(bar) : "memory");
}
__device__ __forceinline__ void bulk_ld_mc(uint32_t dst, const void* src, int bytes, uint32_t bar) {
  asm volatile("cp.async.bulk.shared::cluster.global.mbarrier::complete_tx::bytes.multicast::cluster [%0], [%1], %2, [%3], %4;"
               ::"r"(dst), "l"(src), "r"(bytes), "r"(bar), "h"((uint16_t)3) : "memory");
}
__device__ __forceinline__ void tma2d_st(const CUtensorMap* m, uint32_t src, int c0, int c1) {
  asm volatile("cp.async.bulk.tensor.2d.global.shared::cta.bulk_group [%0, {%2, %3}], [%1];" ::"l"(m), "r"(src), "r"(c0), "r"(c1) : "memory");
}
__device__ __forceinline__ void pf_l2(const void* p, int bytes) { asm volatile("cp.async.bulk.prefetch.L2.global [%0], %1;" ::"l"(p), "r"(bytes) : "memory"); }
__device__ __forceinline__ void pf_t2d(const CUtensorMap* m, int c0, int c1) {
  asm volatile("cp.async.bulk.prefetch.tensor.2d.L2.global [%0, {%1, %2}];" ::"l"(m), "r"(c0), "r"(c1) : "memory");
}
__device__ __forceinline__ void pf_t3d(const CUtensorMap* m, int c0, int c1, int c2) {
  asm volatile("cp.async.bulk.prefetch.tensor.3d.L2.global [%0, {%1, %2, %3}];" ::"l"(m), "r"(c0), "r"(c1), "r"(c2) : "memory");
}
__device__ __forceinline__ void ldsm4(uint32_t (&r)[4], uint32_t a) {
  asm volatile("ldmatrix.sync.aligned.m8n8.x4.shared.b16 {%0,%1,%2,%3}, [%4];" : "=r"(r[0]), "=r"(r[1]), "=r"(r[2]), "=r"(r[3]) : "r"(a) : "memory");
}
__device__ __forceinline__ void ldsm4t(uint32_t (&r)[4], uint32_t a) {
  asm volatile("ldmatrix.sync.aligned.m8n8.x4.trans.shared.b16 {%0,%1,%2,%3}, [%4];" : "=r"(r[0]), "=r"(r[1]), "=r"(r[2]), "=r"(r[3]) : "r"(a) : "memory");
}
__device__ __forceinline__ void stsm4(uint32_t a, uint32_t r0, uint32_t r1, uint32_t r2, uint32_t r3) {
  asm volatile("stmatrix.sync.aligned.m8n8.x4.shared.b16 [%0], {%1,%2,%3,%4};" ::"r"(a), "r"(r0), "r"(r1), "r"(r2), "r"(r3) : "memory");
}
__device__ __forceinline__ uint32_t pk2(float lo, float hi) { uint32_t r; asm("cvt.rn.bf16x2.f32 %0, %1, %2;" : "=r"(r) : "f"(hi), "f"(lo)); return r; }
__device__ __forceinline__ uint32_t hmul(uint32_t a, uint32_t b) { uint32_t r; asm("mul.rn.bf16x2 %0, %1, %2;" : "=r"(r) : "r"(a), "r"(b)); return r; }
__device__ __forceinline__ uint32_t hadd(uint32_t a, uint32_t b) { uint32_t r; asm("add.rn.bf16x2 %0, %1, %2;" : "=r"(r) : "r"(a), "r"(b)); return r; }
__device__ __forceinline__ uint32_t hmax(uint32_t a, uint32_t b) { uint32_t r; asm("max.bf16x2 %0, %1, %2;" : "=r"(r) : "r"(a), "r"(b)); return r; }
__device__ __forceinline__ uint32_t hmin(uint32_t a, uint32_t b) { uint32_t r; asm("min.bf16x2 %0, %1, %2;" : "=r"(r) : "r"(a), "r"(b)); return r; }
__device__ __forceinline__ uint32_t hmaxabs(uint32_t a, uint32_t b) { uint32_t r; asm("max.xorsign.abs.bf16x2 %0, %1, %2;" : "=r"(r) : "r"(a), "r"(b)); return r; }
__device__ __forceinline__ float ex2(float x) { float r; asm("ex2.approx.ftz.f32 %0, %1;" : "=f"(r) : "f"(x)); return r; }
__device__ __forceinline__ float rcp_fast(float x) { float r; asm("rcp.approx.ftz.f32 %0, %1;" : "=f"(r) : "f"(x)); return r; }
__device__ __forceinline__ uint32_t phi2(float lo, float hi) {
  uint32_t t;
  asm("cvt.rn.relu.bf16x2.f32 %0, %1, %2;" : "=r"(t) : "f"(hi), "f"(lo));
  const uint32_t e = pk2(ex2(lo * 1.4426950408889634f), ex2(hi * 1.4426950408889634f));
  return hadd(hadd(t, hmin(e, 0x3F803F80u)), 0x35863586u);
}
__device__ __forceinline__ bool opaque_true() { uint32_t v; asm volatile("mov.u32 %0, %%nctaid.y;" : "=r"(v)); return v != 0; }
__device__ __forceinline__ int norm_exp(uint32_t (&v)[32], float f0) {
  uint32_t m[4] = {hmaxabs(__float_as_uint(f0) >> 16, v[0]), v[1], v[2], v[3]};
#pragma unroll
  for (int i = 4; i < 32; i++) m[i & 3] = hmaxabs(m[i & 3], v[i]);
  m[0] = hmaxabs(hmaxabs(m[0], m[1]), hmaxabs(m[2], m[3]));
  const int e = min(max((int)(__reduce_max_sync(~0u, max(m[0] & 0x7FFFu, (m[0] >> 16) & 0x7FFFu)) >> 7), 1), 253);
  if (e > 141) {
#pragma unroll
    for (int i = 0; i < 32; i++) v[i] = hmul(v[i], 0x07000700u);
  }
  return e;
}
template <int I0, int I1>
__device__ __forceinline__ void norm_cvt(uint32_t (&v)[32], float f0, int e) {
  const uint32_t sc = (e > 141 ? 255 - e : 142 - e) * 0x00800080u;
#pragma unroll
  for (int i = I0; i < I1; i++) {
    const uint32_t a = hmul(v[i], sc);
    v[i] = (a & 0x0FFF0FFFu) * 7 + a;
  }
  if (I0 == 0) v[0] = __byte_perm(v[0], __half_as_ushort(__float2half_rn(f0 * __uint_as_float((254 - e) << 23))), 0x3254);
}
__device__ __forceinline__ void poll_ge(const unsigned* p, unsigned target) {
#pragma unroll 1
  for (int n = 0; n < SPIN_LIMIT; n++) {
    unsigned v;
    asm volatile("ld.relaxed.gpu.global.u32 %0, [%1];" : "=r"(v) : "l"(p) : "memory");
    if (__all_sync(~0u, (int)(v - target) >= 0)) { asm volatile("fence.acquire.gpu;" ::: "memory"); return; }
  }
  __trap();
}

__device__ __forceinline__ bool elect_one() {
  uint32_t p;
  asm volatile("{\n.reg .pred p;\nelect.sync _|p, 0xffffffff;\nselp.u32 %0, 1, 0, p;\n}\n" : "=r"(p));
  return p;
}
__device__ __forceinline__ uint4 ld_nc4(const void* p) {
  uint4 v;
  asm volatile("ld.global.nc.L1::no_allocate.v4.u32 {%0,%1,%2,%3}, [%4];" : "=r"(v.x), "=r"(v.y), "=r"(v.z), "=r"(v.w) : "l"(p));
  return v;
}
__device__ __forceinline__ void st_cg4(void* p, uint4 v) {
  asm volatile("st.global.cg.v4.u32 [%0], {%1,%2,%3,%4};" ::"l"(p), "r"(v.x), "r"(v.y), "r"(v.z), "r"(v.w) : "memory");
}
__device__ __forceinline__ uint32_t mapa(uint32_t a, uint32_t cta) { uint32_t r; asm("mapa.shared::cluster.u32 %0, %1, %2;" : "=r"(r) : "r"(a), "r"(cta)); return r; }
__device__ __forceinline__ void st_async(uint32_t a, uint32_t v, uint32_t bar) {
  asm volatile("st.async.weak.shared::cluster.mbarrier::complete_tx::bytes.b32 [%0], %1, [%2];" ::"r"(a), "r"(v), "r"(bar) : "memory");
}
__device__ __forceinline__ void st_async4(uint32_t a, uint32_t x, uint32_t y, uint32_t z, uint32_t w, uint32_t bar) {
  asm volatile("st.async.weak.shared::cluster.mbarrier::complete_tx::bytes.v4.b32 [%0], {%1,%2,%3,%4}, [%5];" ::"r"(a), "r"(x), "r"(y), "r"(z), "r"(w), "r"(bar) : "memory");
}
__device__ __forceinline__ void tma3d_st(const CUtensorMap* m, uint32_t src, int c0, int c1, int c2) {
  asm volatile("cp.async.bulk.tensor.3d.global.shared::cta.bulk_group [%0, {%2, %3, %4}], [%1];" ::"l"(m), "r"(src), "r"(c0), "r"(c1), "r"(c2) : "memory");
}
__device__ __forceinline__ uint4 ld_rlx4(const void* p) {
  uint4 v;
  asm volatile("{\n.reg .b128 t;\n.reg .b64 a, b;\nld.relaxed.gpu.global.b128 t, [%4];\nmov.b128 {a, b}, t;\nmov.b64 {%0, %1}, a;\nmov.b64 {%2, %3}, b;\n}\n"
               : "=r"(v.x), "=r"(v.y), "=r"(v.z), "=r"(v.w) : "l"(p) : "memory");
  return v;
}
__device__ __forceinline__ void ld_stale4(uint4& v, const void* p, uint32_t tag) {
  asm volatile("{\n.reg .b128 t;\n.reg .b64 a, b;\n.reg .b32 x;\n.reg .pred p;\n"
               "lop3.b32 x, %0, %5, 1, 0x28;\nsetp.ne.u32 p, x, 0;\n"
               "mov.b64 a, {%0, %1};\nmov.b64 b, {%2, %3};\nmov.b128 t, {a, b};\n"
               "@p ld.relaxed.gpu.global.b128 t, [%4];\n"
               "mov.b128 {a, b}, t;\nmov.b64 {%0, %1}, a;\nmov.b64 {%2, %3}, b;\n}\n"
               : "+r"(v.x), "+r"(v.y), "+r"(v.z), "+r"(v.w) : "l"(p), "r"(tag) : "memory");
}
__device__ __forceinline__ void st_tag4(void* p, float a, float b, float c, float d, uint32_t tag) {
  asm volatile("{\n.reg .b128 t;\n.reg .b64 a, b;\nmov.b64 a, {%1, %2};\nmov.b64 b, {%3, %4};\nmov.b128 t, {a, b};\nst.relaxed.gpu.global.b128 [%0], t;\n}\n"
               ::"l"(p), "r"((__float_as_uint(a) & ~1u) | tag), "f"(b), "f"(c), "f"(d) : "memory");
}
__device__ __forceinline__ uint32_t stale8(const uint4 (&f)[8], uint32_t tag) {
  uint32_t r[4];
#pragma unroll
  for (int i = 0; i < 4; i++) asm("lop3.b32 %0, %1, %2, %3, 0x7E;" : "=r"(r[i]) : "r"(f[2 * i].x), "r"(f[2 * i + 1].x), "r"(tag));
  asm("lop3.b32 %0, %0, %1, %2, 0xFE;" : "+r"(r[0]) : "r"(r[1]), "r"(r[2]));
  return r[0] | r[3];
}

struct ConvC { uint32_t a1[2][4], wa[2], wb[2], sg; };
__device__ __forceinline__ uint64_t dsc(uint32_t lo, uint32_t hi) { return ((uint64_t)hi << 32) | lo; }
__device__ __forceinline__ uint32_t hfma(uint32_t a, uint32_t b, uint32_t c) { uint32_t r; asm("fma.rn.f16x2 %0, %1, %2, %3;" : "=r"(r) : "r"(a), "r"(b), "r"(c)); return r; }
__device__ __forceinline__ uint32_t hfnma(uint32_t a, uint32_t b, uint32_t c) { uint32_t r; asm("{.reg .b32 n; neg.f16x2 n, %1; fma.rn.f16x2 %0, n, %2, %3;}" : "=r"(r) : "r"(a), "r"(b), "r"(c)); return r; }
__device__ __forceinline__ uint32_t hmul16(uint32_t a, uint32_t b) { uint32_t r; asm("mul.rn.f16x2 %0, %1, %2;" : "=r"(r) : "r"(a), "r"(b)); return r; }
template <int N> __device__ __forceinline__ void keepu(uint32_t (&d)[N]) {
#pragma unroll
  for (int i = 0; i < N; i++) asm volatile("" : "+r"(d[i])::"memory");
}
__device__ __forceinline__ void conv_m1(const ConvC& K, uint32_t (&u)[16], uint32_t l) {
  wg_fence();
  wgmma_hrs_n64<1>(u, K.a1[0][0], K.a1[0][1], K.a1[0][2], K.a1[0][3], dsc(l, 32), 0);
  wgmma_hrs_n64<1>(u, K.a1[1][0], K.a1[1][1], K.a1[1][2], K.a1[1][3], dsc(l + 16, 32), 1);
  wg_commit();
}
__device__ __forceinline__ void conv_s2(const ConvC& K, uint32_t (&u)[16], uint32_t (&Z)[2][8], uint32_t dfl) {
  uint32_t fr[8], fi[8];
#pragma unroll
  for (int c = 0; c < 8; c++) {
    const uint32_t r = hfma(K.wa[c & 1], u[2 * c + 1], u[2 * c]);
    fi[c] = hfma(K.wb[c & 1], r, u[2 * c + 1]);
    fr[c] = hfma(K.wa[c & 1], fi[c], r);
  }
  wg_fence();
#pragma unroll
  for (int p = 0; p < 2; p++) {
    wgmma_hrs_n32<0>(Z[p], fr[4 * p], fr[4 * p + 2], fr[4 * p + 1], fr[4 * p + 3], dsc(dfl, 32), 0);
    wgmma_hrs_n32<0>(Z[p], fi[4 * p], fi[4 * p + 2], fi[4 * p + 1], fi[4 * p + 3], dsc(dfl + 16, 32), 1);
  }
  wg_commit();
}
__device__ __forceinline__ void conv_win(const ConvC& K, const uint32_t (&X)[2][8], uint32_t (&W)[2][8]) {
#pragma unroll
  for (int b = 0; b < 4; b++)
#pragma unroll
    for (int c = 0; c < 2; c++) {
      const uint32_t xr = X[b >> 1][2 * c + (b & 1)], xi = X[b >> 1][4 + 2 * c + (b & 1)];
      const int a = b ? b - 1 : 0;
      W[b >> 1][2 * c + (b & 1)] = b ? hfnma(K.sg, X[a >> 1][4 + 2 * c + (a & 1)], xr) : hmul16(xr, 0x3C003C00u);
      W[b >> 1][4 + 2 * c + (b & 1)] = b ? hfma(K.sg, X[a >> 1][2 * c + (a & 1)], xi) : hmul16(xi, 0x3C003C00u);
    }
}
template <int p>
__device__ __forceinline__ void conv_pw(uint32_t (&X)[2][8], uint32_t (&H)[2][8], uint32_t (&V)[8], uint32_t dil) {
  uint32_t pr[2][2], pi[2][2];
#pragma unroll
  for (int jj = 0; jj < 2; jj++)
#pragma unroll
    for (int c = 0; c < 2; c++) {
      const int j = 2 * p + jj;
      uint32_t sr = 0, si = 0;
#pragma unroll
      for (int a = 0; a <= j; a++) {
        const int b = j - a;
        const uint32_t hr = H[a >> 1][2 * c + (a & 1)], hi = H[a >> 1][4 + 2 * c + (a & 1)];
        const uint32_t xr = X[b >> 1][2 * c + (b & 1)], xi = X[b >> 1][4 + 2 * c + (b & 1)];
        sr = a == 0 ? hmul16(hr, xr) : hfma(hr, xr, sr);
        si = a == 0 ? hmul16(hr, xi) : hfma(hr, xi, si);
        sr = hfnma(hi, xi, sr);
        si = hfma(hi, xr, si);
      }
      pr[jj][c] = sr; pi[jj][c] = si;
    }
  wg_fence();
  wgmma_hrs_n32<0>(V, pr[0][0], pr[1][0], pr[0][1], pr[1][1], dsc(dil, 32), 0);
  wgmma_hrs_n32<0>(V, pi[0][0], pi[1][0], pi[0][1], pi[1][1], dsc(dil + 16, 32), 1);
  wg_commit();
}
template <int p>
__device__ __forceinline__ void conv_it(const ConvC& K, uint32_t (&V)[8], uint32_t vst) {
#pragma unroll
  for (int jj = 0; jj < 2; jj++) {
    uint32_t wr[2], wi[2];
#pragma unroll
    for (int c = 0; c < 2; c++) {
      const uint32_t r = hfnma(K.wa[c], V[4 + 2 * c + jj], V[2 * c + jj]);
      wi[c] = hfnma(K.wb[c], r, V[4 + 2 * c + jj]);
      wr[c] = hfnma(K.wa[c], wi[c], r);
    }
    stsm4(vst + (2 * p + jj) * 2048, wr[0], wr[1], wi[0], wi[1]);
  }
}
__device__ __forceinline__ void conv_m4(uint32_t (&y)[8], uint32_t (&a)[4][4], uint32_t d4l) {
  wg_fence();
  wgmma_hrs_n32<0>(y, a[0][0], a[0][1], a[0][2], a[0][3], dsc(d4l, 64), 0);
#pragma unroll
  for (int s = 1; s < 4; s++) wgmma_hrs_n32<0>(y, a[s][0], a[s][1], a[s][2], a[s][3], dsc(d4l + s * 16, 64), 1);
  wg_commit();
}

struct Params {
  CUtensorMap tmX, tmW, tmWo, tmWo1, tmK, tmV, tmQ, tmOA, tmOB;
  const __nv_bfloat16 *shift_k, *h, *D, *x, *w, *wo, *q;
  float *part, *kv;
  uint4* o;
  unsigned *ocnt, *epoch;
  const uint32_t *thr, *img;
};

__global__ void __cluster_dims__(2, 1, 1) __launch_bounds__(384, 1) fused_kernel(const __grid_constant__ Params P) {
  extern __shared__ __align__(1024) uint8_t smem[];
  const uint32_t sb = __shfl_sync(~0u, smem_u32(smem), 0);
  const uint32_t bars = sb + OFF_BAR;
  const int tid = threadIdx.x, lane = tid & 31;
  const int warp = __shfl_sync(~0u, tid >> 5, 0);
  const int rank = blockIdx.x & 1, cl = blockIdx.x >> 1;
  const int mb = cl < 4 ? 4 + cl : cl < 36 ? (cl - 4) >> 3 : 4 + (cl - 36) / 7;
  const int hb = (cl - 36) % 7;
  const int hq = cl < 4 ? A0COL : cl < 36 ? (cl - 4) & 7 : hb + (hb >= A0COL);
  const int hp = 2 * hq + rank;
  const int rb = 2 * mb + (hq >> 2), cb = hq & 3;
#define BAR(i) (bars + 8 * (i))

  if (tid == 0) { STAMP(0, 0); GSTAMP(0, 30); }
  if (warp == 8) {
    if (elect_one()) {
      mbar_init(BAR(B_FULL1), 1);
      asm volatile("fence.mbarrier_init.release.cluster;" ::: "memory");
      mbar_expect(BAR(B_FULL1), STAGE_BYTES);
      tma3d(sb + 32768, &P.tmW, hp * 64, 0, 0, BAR(B_FULL1));
    }
    if (lane == 0) STAMP(3, 21);
  } else if (lane == 0) {
    const int wi = warp - (warp > 8);
#pragma unroll
    for (int r = 0; r < 6; r++)
      if (r < 5 || wi < B_COUNT - 56) mbar_init(BAR(1 + 11 * r + wi), ((uint32_t)(bar_counts(r) >> (4 * wi)) & 15) + 1);
    asm volatile("fence.mbarrier_init.release.cluster;" ::: "memory");
  }
  if (tid == 0) STAMP(2, 6);
  asm volatile("barrier.cluster.arrive.relaxed.aligned;\nbarrier.cluster.wait.aligned;" ::: "memory");
  if (warp == 8 && elect_one()) tma2d_mc(sb + rank * 16384, &P.tmX, 0, mb * 256 + rank * 128, BAR(B_FULL1));
  if (tid == 256) STAMP(2, 7);

  if (warp < 8) {
    asm volatile("setmaxnreg.inc.sync.aligned.u32 224;");
    const int wg = warp >> 2, w = warp & 3, g = lane >> 2, q = lane & 3, t = tid & 127;
    const bool elect = (t == 0);
    const uint32_t s16 = (sb & 0x3FFFF) >> 4;
    uint32_t pq[2][16];
    ConvC K;
    {
      float acc[2][96];
      int st = 0, ph = 0;
#pragma unroll 1
      for (int kb = 0; kb < 14; kb++) {
        mbar_wait(BAR(B_FULL1 + st), ph);
        if (kb == 0 && elect) { STAMP(wg, 1); GSTAMP(wg, 26); }
        if (kb == 8 && elect) { STAMP(wg, 16); GSTAMP(wg, 25); }
        const uint32_t da = s16 + st * (STAGE_BYTES >> 4) + wg * 1024 + (1 << 16);
        const uint32_t db = s16 + st * (STAGE_BYTES >> 4) + 2048 + (512 << 16);
        wg_fence();
#pragma unroll
        for (int ks = 0; ks < 4; ks++) {
          wgmma_ss_n192<0, 1>(acc[0], dsc(da + ks * 2, SW128), dsc(db + ks * 128, SW128), (kb | ks) != 0);
          wgmma_ss_n192<0, 1>(acc[1], dsc(da + 512 + ks * 2, SW128), dsc(db + ks * 128, SW128), (kb | ks) != 0);
        }
        wg_commit();
        wg_wait<1>();
        if (kb > 0 && t < 2) mbar_arrive_cl(BAR(B_EMPTY1 + (st == 0 ? 2 : st - 1)), t);
        if (++st == 3) { st = 0; ph ^= 1; }
      }
#define TAIL_MMA(mt, stage) do { wg_fence(); _Pragma("unroll") for (int ks = 0; ks < 4; ks++) \
        wgmma_ss_n192<0, 1>(acc[mt], dsc(s16 + (stage) * (STAGE_BYTES >> 4) + wg * 1024 + (mt) * 512 + (1 << 16) + ks * 2, SW128), \
                            dsc(s16 + (stage) * (STAGE_BYTES >> 4) + 2048 + (512 << 16) + ks * 128, SW128), 1); wg_commit(); } while (0)
      mbar_wait(BAR(B_FULL1 + 2), 0);
      TAIL_MMA(0, 2);
      wg_wait<1>();
      if (elect) mbar_arrive(BAR(B_SFREE));
      mbar_wait(BAR(B_FULL1 + 0), 1);
      TAIL_MMA(0, 0);
      TAIL_MMA(1, 2);
      const uint32_t lrow = sb + wg * 16384 + (16 * w + 8 * ((lane >> 3) & 1) + (lane & 7)) * 128 + (((lane >> 4) ^ (lane & 7)) << 4);
#define E1K(mt, i) do { if (opaque_true()) { _Pragma("unroll") for (int j = (i); j < (i) + 2; j++) { \
          const float* a = &acc[mt][32 + 8 * j]; const float* b = a + 32; const uint32_t o = (lrow ^ (j * 32)) + (mt) * 8192; \
          stsm4(o + 2 * STAGE_BYTES, pk2(b[0], b[1]), pk2(b[2], b[3]), pk2(b[4], b[5]), pk2(b[6], b[7])); \
          stsm4(o, phi2(a[0], a[1]), phi2(a[2], a[3]), phi2(a[4], a[5]), phi2(a[6], a[7])); } } } while (0)
#define E1Q(mt) do { if (opaque_true()) { _Pragma("unroll") for (int i = 0; i < 16; i++) pq[mt][i] = phi2(acc[mt][2 * i], acc[mt][2 * i + 1]); } } while (0)
#define PK_READY(mt) do { fence_async(); __syncwarp(); if (lane == 0) mbar_arrive(BAR(B_PKRDY + (mt))); } while (0)
      wg_wait<1>();
      keep(acc[0]);
      if (elect) STAMP(wg, 18);
      E1K(0, 0);
      TAIL_MMA(1, 0);
      E1K(0, 2);
      if (elect) STAMP(wg, 19);
      PK_READY(0);
      wg_wait<0>();
      keep(acc[1]);
      asm volatile("setmaxnreg.dec.sync.aligned.u32 200;");
      if (elect) { STAMP(wg, 2); GSTAMP(wg, 27); }
      E1K(1, 0);
      E1K(1, 2);
      PK_READY(1);
      if (elect) STAMP(wg, 3);
      {
        const uint4* ct = (const uint4*)P.thr + t;
#pragma unroll
        for (int s = 0; s < 2; s++) { const uint4 u = ld_nc4(ct + s * 128); K.a1[s][0] = u.x; K.a1[s][1] = u.y; K.a1[s][2] = u.z; K.a1[s][3] = u.w; }
        const uint4 u = ld_nc4(ct + 2 * 128);
        K.wa[0] = u.x; K.wa[1] = u.y; K.wb[0] = u.z; K.wb[1] = u.w;
        K.sg = (lane & 4) ? 0xBC00BC00u : 0x3C003C00u;
      }
      if (CWAIT) mbar_wait(BAR(B_PKFREE), 0);
      if (elect) STAMP(wg, 4);
      E1Q(0);
      E1Q(1);
    }
    if (elect) STAMP(wg, 17);
    mbar_wait(BAR(B_H), 0);
    mbar_wait(BAR(B_PKRDY + 1), 0);
    if (elect) STAMP(wg, 5);
    {
      const uint32_t dfl = s16 + (OFF_F2F >> 4) + (8 << 16), dil = s16 + (OFF_F2I >> 4) + (8 << 16), d4l = s16 + (OFF_F4 >> 4) + (8 << 16);
      const uint32_t xl = s16 + (OFF_XT >> 4) + 4 * wg * (XT_STRIDE >> 4) + (8 << 16);
      const uint32_t hl = s16 + (OFF_H >> 4) + wg * 512 + (8 << 16);
      uint32_t vst = sb + wg * 8192 + w * 512 + lane * 16, vld = sb + wg * 8192 + w * 2048 + lane * 16;
      uint32_t ya = mapa(sb + OFF_XT + 4 * wg * XT_STRIDE + (2 * rank + (w & 1)) * 1024 + lane * 16, w >> 1);
      const uint32_t ybar = mapa(BAR(B_Y), w >> 1);
      asm volatile("" : "+r"(vst), "+r"(vld), "+r"(ya));
      uint32_t ux[16], uh[16], W[2][8], V0[8], V1[8], y[8], a[4][4];
      uint4* const ot = P.o + ((2 * mb + wg) * 16 + hq) * 1024 + (16 * w + g) * 8 + ((4 * rank + q) ^ g);
#define YOUT(i) do { if ((w >> 1) == rank) { \
          asm volatile("st.shared.v4.b32 [%0], {%1,%2,%3,%4};" ::"r"(ya + (i) * XT_STRIDE), "r"(y[0]), "r"(y[2]), "r"(y[4]), "r"(y[6]) : "memory"); \
          asm volatile("st.shared.v4.b32 [%0], {%1,%2,%3,%4};" ::"r"(ya + (i) * XT_STRIDE + 512), "r"(y[1]), "r"(y[3]), "r"(y[5]), "r"(y[7]) : "memory"); \
        } else { \
          mbar_wait(BAR(B_XFREE + 4 * wg + (i)), 0); \
          st_async4(ya + (i) * XT_STRIDE, y[0], y[2], y[4], y[6], ybar); \
          st_async4(ya + (i) * XT_STRIDE + 512, y[1], y[3], y[5], y[7], ybar); } } while (0)
      auto ocalc = [&](const int hh) {
        if (hh == 0) {
          if (elect) STAMP(wg, 8);
          mbar_wait(BAR(B_KV), 0);
          if (elect) STAMP(wg, 9);
        }
        float oa[2][20];
        wg_fence();
#pragma unroll
        for (int m = 0; m < 4; m++) {
          const uint32_t* p = &pq[m & 1][8 * hh + 4 * (m >> 1)];
          wgmma_rs_n40<1>(oa[m & 1], p[0], p[1], p[2], p[3], dsc(s16 + (OFF_KVB >> 4) + hh * 160 + (m >> 1) * 16 + (8 << 16), 32), m >> 1);
        }
        wg_commit();
        wg_wait<0>();
#pragma unroll
        for (int mt = 0; mt < 2; mt++) {
          float (&o)[20] = oa[mt];
          keep(o);
          const uint32_t den = hadd(pk2(o[16], o[18]), 0x35863586u);
#pragma unroll
          for (int r = 0; r < 2; r++) {
            const float ri = rcp_fast(__uint_as_float(r ? (den & 0xFFFF0000u) : (den << 16)));
            uint4 u;
            u.x = pk2(o[2 * r] * ri, o[2 * r + 1] * ri);
            u.y = pk2(o[4 + 2 * r] * ri, o[5 + 2 * r] * ri);
            u.z = pk2(o[8 + 2 * r] * ri, o[9 + 2 * r] * ri);
            u.w = pk2(o[12 + 2 * r] * ri, o[13 + 2 * r] * ri);
            st_cg4(ot + hh * 8 * 1024 + (64 * mt + 8 * r) * 8, u);
          }
        }
        __syncwarp();
        if (lane == 0) mbar_arrive(BAR(hh ? B_ODONE1 : B_ODONE));
        if (hh == 0 && elect) STAMP(wg, 10);
      };
      uint32_t X[4][2][8], H[4][2][8];
      conv_m1(K, ux, xl);
      conv_m1(K, uh, hl);
      wg_wait<1>(); keepu(ux);
      if (lane == 0) mbar_arrive_cl(BAR(B_XFREE + 4 * wg), rank ^ 1);
      conv_s2(K, ux, X[0], dfl);
      wg_wait<1>(); keepu(uh);
      conv_s2(K, uh, H[0], dfl);
#pragma unroll
      for (int i = 0; i < 4; i++) {
        const bool nx = i < 3;
        const int n = nx ? i + 1 : i;
        const uint32_t vo = (i & 1) ? OFF_H + (i >> 1) * 16384 : OFF_VP;
        if (2 * i == OCH) ocalc(0);
        if (2 * i == OCH + O1D) ocalc(1);
        if (nx) {
          if (n == 2) mbar_wait(BAR(B_H2), 0);
          conv_m1(K, ux, xl + n * (XT_STRIDE >> 4));
          conv_m1(K, uh, hl + (n >> 1) * 1024 + (n & 1) * 256);
        }
        if (2 * i != OCH && 2 * i != OCH + O1D) { if (nx) { if (i > 0) wg_wait<3>(); else wg_wait<2>(); } else wg_wait<1>(); }
        keepu(X[i][0]); keepu(X[i][1]); keepu(H[i][0]); keepu(H[i][1]);
        conv_win(K, X[i], W);
        conv_pw<0>(W, H[i], V0, dil);
        conv_pw<1>(W, H[i], V1, dil);
        wg_wait<2>();
        if (i > 0) { keepu(y); YOUT(i - 1); }
        if (2 * i + 1 == OCH) ocalc(0);
        if (2 * i + 1 == OCH + O1D) ocalc(1);
        if (nx) {
          keepu(ux); keepu(uh);
          if (lane == 0) mbar_arrive_cl(BAR(B_XFREE + 4 * wg + n), rank ^ 1);
          conv_s2(K, ux, X[n], dfl);
          wg_wait<1>();
        } else wg_wait<0>();
        keepu(V0); keepu(V1);
        conv_it<0>(K, V0, vst + vo);
        conv_it<1>(K, V1, vst + vo);
        bar_sync(1 + wg);
#pragma unroll
        for (int s = 0; s < 4; s++) ldsm4t(a[s], vld + vo + s * 512);
        if (nx) conv_s2(K, uh, H[n], dfl);
        conv_m4(y, a, d4l);
        if (i > 0 && lane < 2) mbar_arrive_cl(BAR(B_AFREE + i - 1), lane);
        if (elect && i < 3) STAMP(wg, i < 2 ? 6 + i : 9 + i);
      }
      wg_wait<0>(); keepu(y);
      YOUT(3);
      __syncwarp();
      if (lane == 0) mbar_arrive(BAR(B_Y));
      if (elect) STAMP(wg, 12);
    }
    {
      float acc[64];
#define G2_MMA(da, db, first) do { wg_fence(); _Pragma("unroll") for (int ks = 0; ks < 4; ks++) \
        wgmma_ss_n128<0, 1>(acc, dsc((da) + ks * 2, SW128), dsc((db) + ks * 128, SW128), ks || !(first)); wg_commit(); } while (0)
      const uint32_t a0 = s16 + wg * 512 + (1 << 16), b0 = s16 + (512 << 16);
      uint64_t ta = SLOT_A, tb = SLOT_B;
      uint32_t da = a0 + (SLOT_A & 15) * 1024, db = b0 + (SLOT_B & 15) * 1024, fb = BAR(B_FULL2);
      uint32_t cons = mapa(BAR(B_CONS2 - 1), t & 1);
      const bool rel = __shfl_sync(~0u, t, lane) < 2;
#pragma unroll 1
      for (int kb = 0; kb < 13; kb++) {
        if (G2S == 0 && tid == 128) STAMP(2, 8 + kb);
        mbar_wait(fb, 0);
        if (G2S == 1 && tid == 128) STAMP(2, 8 + kb);
        if (kb == 0 && elect) { STAMP(wg, 13); GSTAMP(wg, 28); }
        G2_MMA(da, db, kb == 0);
        ta >>= 4; tb >>= 4;
        da = a0 + ((uint32_t)ta & 15) * 1024; db = b0 + ((uint32_t)tb & 15) * 1024; fb += 8;
        asm volatile("" : "+r"(da), "+r"(db));
        wg_wait<1>();
        if (kb > 0 && rel) asm volatile("mbarrier.arrive.shared::cluster.b64 _, [%0];" ::"r"(cons) : "memory");
        cons += 8;
      }
#pragma unroll
      for (int kb = 13; kb < 16; kb++) {
        if (wg == 1) mbar_wait(BAR(B_FULL2 + kb), 0);
        else if (kb == 13) asm volatile("bar.sync 3, 256;" ::: "memory");
        G2_MMA(a0 + ((SLOT_A >> (4 * kb)) & 15) * 1024, b0 + ((SLOT_B >> (4 * kb)) & 15) * 1024, false);
      }
      if (wg == 1) asm volatile("bar.arrive 3, 256;" ::: "memory");
      wg_wait<0>();
      keep(acc);
      if (elect) { STAMP(wg, 14); GSTAMP(wg, 29); }
      mbar_wait(BAR(B_CONS2 + 11), 0);
      const uint32_t stg = sb + ((uint32_t)((wg ? SLOT_A : SLOT_B) >> 44) & 15) * 16384;
      const uint32_t lrow = stg + (16 * w + 8 * ((lane >> 3) & 1) + (lane & 7)) * 128 + (((lane >> 4) ^ (lane & 7)) << 4);
#pragma unroll
      for (int cp = 0; cp < 8; cp++) {
        const float* a = &acc[8 * cp];
        stsm4((lrow ^ ((cp & 3) * 32)) + (cp >> 2) * 8192, pk2(a[0], a[1]), pk2(a[2], a[3]), pk2(a[4], a[5]), pk2(a[6], a[7]));
      }
      fence_async();
      bar_sync(1 + wg);
      if (elect) {
        const int col = 1024 + 256 * cb + 128 * rank, row = 128 * rb + 64 * wg;
        tma2d_st(&P.tmOB, stg, col, row);
        tma2d_st(&P.tmOB, stg + 8192, col + 64, row);
        asm volatile("cp.async.bulk.commit_group;\ncp.async.bulk.wait_group.read 0;" ::: "memory");
        STAMP(wg, 15); GSTAMP(wg, 31); PDUMP(wg); if (wg == 0) PDUMP(2);
      }
    }
  } else {
    asm volatile("setmaxnreg.dec.sync.aligned.u32 56;");
    const int hw = warp - 9, g = lane >> 2, q = lane & 3;
#define sbar (bars + 8 * (B_STG - 18) + 16 * warp)
    if (warp == 8) {
      int st = 1, pp = 1;
      const uint8_t* pfx = (const uint8_t*)P.x + (mb * 256 + hp * 16 + (lane & 15)) * 2048;
      const uint8_t* pfw = (const uint8_t*)P.w + (mb * 8 + (lane & 7)) * 6144 + (lane >> 3) * 2048 + hp * 128;
#pragma unroll 1
      for (int kb = 1; kb < 16; kb++) {
        if (kb >= 3) mbar_wait(BAR(B_EMPTY1 + st), pp);
        const uint32_t sa = sb + st * STAGE_BYTES;
        if (elect_one()) {
          mbar_expect(BAR(B_FULL1 + st), STAGE_BYTES);
          tma2d_mc(sa + rank * 16384, &P.tmX, kb * 64, mb * 256 + rank * 128, BAR(B_FULL1 + st));
          tma3d(sa + 32768, &P.tmW, hp * 64, kb * 64, 0, BAR(B_FULL1 + st));
        }
        if (kb == 1 && lane == 0) STAMP(2, 24);
        if (PFD && kb >= 2) {
#pragma unroll 1
          for (int j = kb == 2 ? 3 : kb + PFD; j <= kb + PFD && j < 16; j++) {
            if (lane < 16) asm volatile("prefetch.global.L2 [%0];" ::"l"(pfx + j * 128));
            if (lane < 24) asm volatile("prefetch.global.L2 [%0];" ::"l"(pfw + j * (64 * 6144)));
          }
          if (kb >= QPF && kb < QPF + 8) asm volatile("prefetch.global.L2 [%0];" ::"l"((const uint8_t*)P.q + (blockIdx.x * 256 + (kb - QPF) * 32 + lane) * 128));
          if (kb >= 4)
            asm volatile("prefetch.global.L2 [%0];" ::"l"(kb < 12 ? (const uint8_t*)P.h + (blockIdx.x * 256 + (kb - 4) * 32 + lane) * 128
                                                                  : (const uint8_t*)P.wo + (blockIdx.x * 128 + (kb - 12) * 32 + lane) * 128));
        }
        if (++st == 3) { st = 0; pp ^= 1; }
      }
      if (lane == 0) STAMP(2, 1);
    } else {
      {
        const uint32_t clk0 = __shfl_sync(~0u, (uint32_t)clock(), 0), stg = sb + OFF_STG + hw * STG_STRIDE;
        const unsigned epoch = __shfl_sync(~0u, P.epoch[blockIdx.x], 0);
        const uint32_t tag = ~epoch & 1;
        uint32_t tap[2][4];
#pragma unroll
        for (int cg = 0; cg < 2; cg++) {
          const uint2 u = __ldg((const uint2*)(P.shift_k + (16 * cl + 8 * cg + g) * 4));
          tap[cg][0] = __byte_perm(u.x, 0, 0x1010); tap[cg][1] = __byte_perm(u.x, 0, 0x3232);
          tap[cg][2] = __byte_perm(u.y, 0, 0x1010); tap[cg][3] = __byte_perm(u.y, 0, 0x3232);
        }
        if (hw == 0 && lane < 8) *(float*)(smem + OFF_D + 4 * lane) = __bfloat162float(P.D[blockIdx.x * 8 + lane]);
        if (hw == 1) asm volatile("prefetch.global.L2 [%0];" ::"l"(P.thr + (lane + 32 * (blockIdx.x & 1)) * 32));
        if (hw == 0 && elect_one()) {
          *(volatile unsigned*)(smem + OFF_EPOCH) = epoch;
          mbar_expect(BAR(B_XRAW), 16384);
          mbar_expect(BAR(B_Y), 16384 + 64);
        }
        for (int i = hw * 32 + lane; i < 528; i += 96) st_tag4(P.part + (hp * 8 + mb) * 2176 + 4 * i, 0.f, 0.f, 0.f, 0.f, tag ^ 1);
        if (hw < 2 || lane < 2) st_tag4(P.kv + hp * 2176 + (4 * (hw < 2 ? 64 * mb + 32 * hw + lane : 512 + 2 * mb + lane)), 0.f, 0.f, 0.f, 0.f, tag ^ 1);
        if (lane == 0) STAMP(3, hw);
        const uint32_t xo = sb + OFF_XT + g * XT_STRIDE + rank * 2048 + q * 4;
        const int krow = 8 + (lane & 7) - (lane >> 3);
        const uint32_t ka = stg + krow * 32 + ((krow & 4) << 2), va = stg + 2304 + lane * 32 + ((lane & 4) << 2);
        int ph = 0, b = 0;
#pragma unroll 1
        for (int ci = hw - 3; ci < 16; ci += 3) {
          const uint32_t bo = b ? OFF_F2F - OFF_STG : 0, bn = b ? 0 : OFF_F2F - OFF_STG;
          if (ci + 3 < 16) {
            while (__any_sync(~0u, (uint32_t)clock() - clk0 < HSTART + (ci + 3) * PACE)) __nanosleep(64);
            if (elect_one()) {
              mbar_expect(sbar + 8 * (b ^ 1), 2304 + 2048);
              tma2d(stg + bn, &P.tmK, 16 * cl, 1024 * rank + 64 * (ci + 3) - 8, sbar + 8 * (b ^ 1));
              tma2d(stg + bn + 2304, &P.tmV, 16 * cl, 1024 * rank + 64 * (ci + 3), sbar + 8 * (b ^ 1));
            }
          }
          if (ci >= 0) {
            mbar_wait(sbar + 8 * b, (ph >> b) & 1);
            ph ^= 1 << b;
#pragma unroll 1
            for (int grp = 0; grp < 2; grp++) {
#pragma unroll
              for (int cg = 0; cg < 2; cg++) {
                const uint32_t dst = mapa(xo + (ci >> 3) * 1024 + ((ci & 7) * 4 + 2 * grp) * 16, cg), xbar = mapa(BAR(B_XRAW), cg);
                uint32_t vv[4], kk[4][4];
                ldsm4t(vv, (va ^ (cg * 16)) + bo + grp * 1024);
#pragma unroll
                for (int rg = 0; rg < 4; rg++) ldsm4t(kk[rg], (ka ^ (cg * 16)) + bo + grp * 1024 + rg * 256);
#pragma unroll
                for (int rg = 0; rg < 4; rg++)
                  vv[rg] = hmul(hadd(hadd(hadd(hmul(kk[rg][3], tap[cg][3]), hmul(kk[rg][2], tap[cg][2])), hmul(kk[rg][1], tap[cg][1])), hmul(kk[rg][0], tap[cg][0])), vv[rg]);
                if (cg == rank) {
#pragma unroll
                  for (int rg = 0; rg < 4; rg++) asm volatile("st.shared.b32 [%0], %1;" ::"r"(dst + (rg & 1) * 512 + (rg >> 1) * 16), "r"(vv[rg]) : "memory");
                } else {
#pragma unroll
                  for (int rg = 0; rg < 4; rg++) st_async(dst + (rg & 1) * 512 + (rg >> 1) * 16, vv[rg], xbar);
                }
              }
            }
          }
          b ^= 1;
        }
      }
      if (lane == 0) STAMP(3, 3 + hw);
      asm volatile("bar.sync 4, 96;" ::: "memory");
      if (hw == 0 && elect_one()) { mbar_expect(BAR(B_XT), 10240); bulk_ld(sb + OFF_F2F, P.img, 10240, BAR(B_XT)); }
      mbar_wait(BAR(B_XRAW), 0);
    }
#pragma unroll 1
    for (int n = hw < 0 ? 3 : 0; n < 4; n++) {
      const bool isH = n >= 3;
      const int c = isH ? (warp & 1) + 2 * (warp & 2) : hw + 3 * n;
      if (c < 8) {
        int ln;
        asm volatile("mov.u32 %0, %%laneid;" : "=r"(ln));
        uint8_t* dst = smem + (isH ? OFF_H + (c & 2) * 8192 + (c >> 2) * 8192 + (c & 1) * 4096 : OFF_XT + c * XT_STRIDE) + ((ln >> 4) * 512 + (ln & 15) * 16);
        const uint8_t* src0 = isH ? (const uint8_t*)P.h + (blockIdx.x * 8 + c) * 4096 + ((ln & 15) * 32 + (ln & 16)) : dst;
        const uint8_t* src1 = src0 + (isH ? 512 : 256);
        uint32_t v[32];
#pragma unroll
        for (int i = 0; i < 8; i++) {
          const uint4 u = *(const uint4*)(((i & 1) ? src1 : src0) + (i >> 1) * 1024);
          v[4 * i] = u.x; v[4 * i + 1] = u.y; v[4 * i + 2] = u.z; v[4 * i + 3] = u.w;
        }
        if (isH) mbar_wait(BAR(B_XT), 0);
        const float f0 = __uint_as_float(v[0] << 16) + ((isH && ln == 0) ? *(const float*)(smem + OFF_D + 4 * c) : 0.f);
        const int e = norm_exp(v, f0);
        norm_cvt<0, 32>(v, f0, e);
        if (isH) {
          if (ln < 2) st_async(mapa(sb + OFF_SCALE + (8 * rank + c) * 4, ln), min(max(e + smem[OFF_EX + c] - 124, 1), 254) << 23, mapa(BAR(B_Y), ln));
          mbar_wait(BAR(B_SFREE), 0);
        } else if (ln == 0) smem[OFF_EX + c] = e;
#pragma unroll
        for (int i = 0; i < 8; i++)
          *(uint4*)(dst + (i >> 1) * 1024 + (i & 1) * 256) = make_uint4(v[4 * i], v[4 * i + 1], v[4 * i + 2], v[4 * i + 3]);
        if (n < 2 && elect_one()) {
          if (n == 0) mbar_expect(sbar, 4096);
          tma3d(sb + OFF_STG + 2048 * c, &P.tmQ, 16 * cl, 64 * rank, 2 * c, sbar);
        }
      }
      if (n >= 2) {
        fence_async();
        __syncwarp();
        if (lane == 0) { mbar_arrive(BAR(isH ? B_H : B_XT)); STAMP(3, (isH ? 17 : 13) + hw); }
      }
    }
#define SLOT(tab, kb) (sb + ((uint32_t)((tab) >> (4 * (kb))) & 15) * 16384)
#define LOAD_B(kb) tma4d(SLOT(SLOT_B, kb), &P.tmWo, 0, ((kb) >> 3) * 32, 2 * ((kb) & 7), 4 * cb + 2 * rank, BAR(B_FULL2 + (kb)))
#define LOAD_A(kb) bulk_ld_mc(SLOT(SLOT_A, kb) + rank * 8192, P.o + (rb * 16 + (kb)) * 1024 + rank * 512, 8192, BAR(B_FULL2 + (kb)))
    asm volatile("setmaxnreg.inc.sync.aligned.u32 104;");
    const unsigned epoch = *(volatile unsigned*)(smem + OFF_EPOCH);
    const uint32_t tag = ~epoch & 1;
    const int pi = hw < 2 ? 64 * mb - 288 + tid : 512 + 2 * mb + (lane & 1);
    const float* psrc = P.part + hp * 8 * 2176 + 4 * pi;
    uint4 f[8];
    {
      const uint32_t s16 = (sb & 0x3FFFF) >> 4;
      const int t = tid & 127, c = 2 + (warp & 1) + 2 * (warp & 2);
      uint32_t v[32];
      const uint4* hp4 = (const uint4*)(P.h + (blockIdx.x * 8 + c) * 2048) + ((lane & 15) * 2 + (lane >> 4));
#pragma unroll
      for (int i = 0; i < 8; i++) { const uint4 u = ld_nc4(hp4 + i * 32); v[4 * i] = u.x; v[4 * i + 1] = u.y; v[4 * i + 2] = u.z; v[4 * i + 3] = u.w; }
      float kva[36];
#pragma unroll
      for (int mt = 0; mt < 2; mt++) {
        mbar_wait(BAR(B_PKRDY + mt), 0);
        wg_fence();
#pragma unroll
        for (int ks = 0; ks < 8; ks++) {
          const uint32_t o = (ks >> 2) * 1024 + mt * 512 + (ks & 3) * 128, vb = (2 * STAGE_BYTES >> 4) + o;
          wgmma_ss_n72<1, 1>(kva, dsc(s16 + o + (1 << 16), SW128), dsc(s16 + vb + (((OFF_ONES >> 4) - vb) << 16), SW128), (mt | ks) != 0);
        }
        wg_commit();
      }
      float* pdst = P.part + (hp * 8 + mb) * 2176 + t * 4;
      float* zdst = P.part + (hp * 8 + mb) * 2176 + 2048 + (t >> 1);
      asm volatile("" : "+l"(pdst), "+l"(zdst));
      wg_wait<0>();
      keep(kva);
      if (hw < 1) {
#pragma unroll
        for (int c = 0; c < 4; c++) st_tag4(pdst + c * 512, kva[4 * c], kva[4 * c + 1], kva[4 * c + 2], kva[4 * c + 3], tag);
      } else {
#pragma unroll
        for (int c = 4; c < 8; c++) st_tag4(pdst + (c - 4) * 512, kva[4 * c], kva[4 * c + 1], kva[4 * c + 2], kva[4 * c + 3], tag);
      }
      const float z2 = __shfl_down_sync(~0u, kva[32], 4), z3 = __shfl_down_sync(~0u, kva[34], 4);
      if (!(lane & 7)) st_tag4(zdst, kva[32], kva[34], z2, z3, tag);
      if (lane == 0) mbar_arrive(BAR(B_PKFREE));
      if (hw == 0 && lane == 0) STAMP(3, 24);
      const float f0 = __uint_as_float(v[0] << 16) + (lane == 0 ? *(const float*)(smem + OFF_D + 4 * c) : 0.f);
      const int e = norm_exp(v, f0);
      if (HSPL > 0) norm_cvt<0, HSPL>(v, f0, e);
      if (hw >= 0) {
        if (hw == 0 && lane == 0) STAMP(3, 20);
#pragma unroll
        for (int p = 0; p < 8; p++) f[p] = ld_rlx4(psrc + p * 2176);
      }
      if (HSPL < 32) norm_cvt<HSPL, 32>(v, f0, e);
      uint8_t* dst = smem + OFF_H + 16384 + (warp & 3) * 4096 + (lane >> 4) * 512 + (lane & 15) * 16;
#pragma unroll
      for (int i = 0; i < 8; i++)
        *(uint4*)(dst + (i >> 1) * 1024 + (i & 1) * 256) = make_uint4(v[4 * i], v[4 * i + 1], v[4 * i + 2], v[4 * i + 3]);
      if (lane < 2) st_async(mapa(sb + OFF_SCALE + (8 * rank + c) * 4, lane), min(max(e + smem[OFF_EX + c] - 124, 1), 254) << 23, mapa(BAR(B_Y), lane));
      fence_async();
      __syncwarp();
      if (lane == 0) mbar_arrive(BAR(B_H2));
    }
    if (warp == 8) {
      mbar_wait(BAR(B_PKFREE), 0);
      {
        const uint32_t c0 = clock();
#pragma unroll 1
        for (int i = 0; i < 14; i++) {
          const int kb = i >> 1;
          while (__any_sync(~0u, (uint32_t)clock() - c0 < i * BPACE)) __nanosleep(32);
          if (elect_one()) {
            if (!(i & 1)) mbar_expect(BAR(B_FULL2 + kb), 16384);
            tma4d(SLOT(SLOT_B, kb) + (i & 1) * 8192, &P.tmWo1, 0, 0, 2 * kb, 4 * cb + 2 * rank + (i & 1), BAR(B_FULL2 + kb));
            if (i == 0) mbar_expect(BAR(B_Q), 8192);
            if (i < 4) tma3d(sb + OFF_SPARE + 2048 * i, &P.tmQ, 16 * cl, 64 * rank + 32 * (i >> 1), 2 * ((i + 6) & 7), BAR(B_Q));
          }
        }
      }
      if (lane == 0) STAMP(2, 2);
      mbar_wait(BAR(B_AFREE), 0);
      if (elect_one()) mbar_expect(BAR(B_FULL2), 16384);
      {
        const uint32_t dst = SLOT(SLOT_A, 0) + rank * 8192;
        const uint4* src = P.o + rb * 16 * 1024 + rank * 512;
        poll_ge(&P.ocnt[rb * 32], 16 * (epoch + 1));
        asm volatile("fence.proxy.async.global;" ::: "memory");
        if (lane == 0) STAMP(2, 3);
        if (elect_one()) bulk_ld_mc(dst, src, 8192, BAR(B_FULL2));
        if (lane == 0) STAMP(3, 23);
      }
#pragma unroll 1
      for (int kb = 1; kb < 7; kb++) {
        mbar_wait(BAR(kb < 3 ? B_AFREE + kb : B_CONS2 + ((kb - 3) >> 1)), 0);
        if (elect_one()) { mbar_expect(BAR(B_FULL2 + kb), 16384); LOAD_A(kb); }
      }
#pragma unroll 1
      for (int kb = 7; kb < 16; kb++) {
        mbar_wait(BAR(B_CONS2 + kb - 5), 0);
        if (kb == 8) mbar_wait(BAR(B_O1RDY), 0);
        if (elect_one()) { mbar_expect(BAR(B_FULL2 + kb), 32768); LOAD_A(kb); LOAD_B(kb); }
      }
      if (lane == 0) { P.epoch[blockIdx.x] = epoch + 1; STAMP(2, 5); }
    } else {
      {
#pragma unroll 1
        for (int n = 0; __any_sync(~0u, stale8(f, tag) & 1); n++) {
#pragma unroll
          for (int p = 0; p < 8; p++) ld_stale4(f[p], psrc + p * 2176, tag);
          if (n > SPIN_LIMIT) __trap();
        }
        float s0 = 0.f, s1 = 0.f, s2 = 0.f, s3 = 0.f;
#pragma unroll
        for (int p = 0; p < 8; p++) { s0 += __uint_as_float(f[p].x); s1 += __uint_as_float(f[p].y); s2 += __uint_as_float(f[p].z); s3 += __uint_as_float(f[p].w); }
        if (hw < 2 || lane < 2) st_tag4(P.kv + hp * 2176 + (4 * pi), s0, s1, s2, s3, tag);
      }
      if (lane == 0 && hw == 0) STAMP(3, 8);
      if (hw == 2) {
        unsigned* cnt = P.ocnt + (2 * mb + lane) * 32;
#pragma unroll 1
        for (int hh = 0; hh < 2; hh++) {
          mbar_wait(BAR(hh ? B_ODONE1 : B_ODONE), 0);
          if (lane < 2) asm volatile("red.release.gpu.global.add.u32 [%0], 1;" ::"l"(cnt + hh * 512) : "memory");
          if (lane == 0) STAMP(3, hh ? 6 : 7);
        }
        poll_ge(&P.ocnt[512 + rb * 32], 16 * (epoch + 1));
        asm volatile("fence.proxy.async.global;" ::: "memory");
        if (lane == 0) { mbar_arrive(BAR(B_O1RDY)); STAMP(2, 4); }
        __syncwarp();
      } else {
        if (PD2) __nanosleep(PD2);
        const int t = tid - 288;
        const float* src = P.kv + hp * 2176 + (4 * t);
        const float* zsrc = P.kv + hp * 2176 + (2048 + (t & 48) + 2 * (lane & 6));
        uint4 zp = ld_rlx4(zsrc);
#pragma unroll
        for (int p = 0; p < 8; p++) f[p] = ld_rlx4(src + 4 * ((p & 3) * 128 + (p >> 2) * 64));
        if (!opaque_true()) __trap();
#pragma unroll 1
        for (int n = 0; __any_sync(~0u, (stale8(f, tag) | (zp.x ^ tag)) & 1); n++) {
          ld_stale4(zp, zsrc, tag);
#pragma unroll
          for (int p = 0; p < 8; p++) ld_stale4(f[p], src + 4 * ((p & 3) * 128 + (p >> 2) * 64), tag);
          if (n > SPIN_LIMIT) __trap();
        }
#define PK2U(a, b) pk2(__uint_as_float(a), __uint_as_float(b))
        const uint32_t zf = (lane & 1) ? ((lane & 8) ? zp.w : zp.z) : ((lane & 8) ? zp.y : zp.x);
        const uint32_t zz = PK2U(zf, zf);
        *(uint4*)(smem + OFF_KVB + hw * 2560 + 2048 + lane * 16) = make_uint4(zz, zz, zz, zz);
        if (!opaque_true()) __trap();
#pragma unroll
        for (int hh = 0; hh < 2; hh++) {
          const uint4* ff = &f[4 * hh];
          uint8_t* dst = smem + OFF_KVB + hh * 2560 + q * 512 + (16 * hw + g) * 16;
          *(uint4*)dst = make_uint4(PK2U(ff[0].x, ff[0].y), PK2U(ff[1].x, ff[1].y), PK2U(ff[2].x, ff[2].y), PK2U(ff[3].x, ff[3].y));
          *(uint4*)(dst + 128) = make_uint4(PK2U(ff[0].z, ff[0].w), PK2U(ff[1].z, ff[1].w), PK2U(ff[2].z, ff[2].w), PK2U(ff[3].z, ff[3].w));
        }
        fence_async();
        __syncwarp();
        if (lane == 0) { mbar_arrive(BAR(B_KV)); if (hw == 0) STAMP(3, 9); }
      }
#define QBUF(ci) (sb + 2048 * (ci) + ((ci) < 6 ? OFF_STG : (ci) < 10 ? OFF_SPARE - 6 * 2048 : OFF_F2F - 10 * 2048))
      mbar_wait(BAR(B_Y), 0);
      if (elect_one()) {
        mbar_expect(sbar + 8, 4096);
#pragma unroll 1
        for (int ci = hw ? hw + 9 : 12; ci < 16; ci += 3) tma3d(QBUF(ci), &P.tmQ, 16 * cl, 64 * rank + 32, 2 * (ci & 7), sbar + 8);
      }
      mbar_wait(BAR(B_Q), 0);
      mbar_wait(sbar, hw == 0);
      {
        const float2 sc0 = *(const float2*)(smem + OFF_SCALE + 8 * q), sc1 = *(const float2*)(smem + OFF_SCALE + 32 + 8 * q);
        const uint32_t yl = sb + OFF_XT + (lane & 7) * XT_STRIDE + (lane >> 3) * 16;
#pragma unroll 1
        for (int ci = hw; ci < 16; ci += 3) {
          const uint32_t qb = QBUF(ci);
          if (ci >= 10) mbar_wait(sbar + 8, 1);
#pragma unroll 1
          for (int nl = 0; nl < 2; nl++) {
            uint32_t yy[2][4], qq[2][4];
            const uint32_t qa = qb + lane * 32 + ((lane & 4) << 2) + nl * 1024;
#pragma unroll
            for (int cg = 0; cg < 2; cg++) { ldsm4t(yy[cg], yl + cg * 2048 + (2 * ci + nl) * 64); ldsm4(qq[cg], qa ^ (cg * 16)); }
#pragma unroll
            for (int cg = 0; cg < 2; cg++) {
              const float2 sc = cg ? sc1 : sc0;
#pragma unroll
              for (int m = 0; m < 4; m++) {
                const float2 f = __half22float2(*(const __half2*)&yy[cg][m]);
                qq[cg][m] = hmul(qq[cg][m], pk2(f.x * sc.x, f.y * sc.y));
              }
              stsm4(qa ^ (cg * 16), qq[cg][0], qq[cg][1], qq[cg][2], qq[cg][3]);
            }
          }
          fence_async();
          __syncwarp();
          if (elect_one()) tma3d_st(&P.tmOA, qb, 16 * cl, 64 * rank + 32 * (ci >> 3), 2 * (ci & 7));
        }
        asm volatile("cp.async.bulk.commit_group;\ncp.async.bulk.wait_group.read 0;" ::: "memory");
      }
      if (lane == 0) STAMP(3, 10 + hw);
    }
  }
}

typedef CUresult (*EncodeFn)(CUtensorMap*, CUtensorMapDataType, cuuint32_t, void*, const cuuint64_t*, const cuuint64_t*,
                             const cuuint32_t*, const cuuint32_t*, CUtensorMapInterleave, CUtensorMapSwizzle,
                             CUtensorMapL2promotion, CUtensorMapFloatOOBfill);

static void enc(EncodeFn fn, CUtensorMap* m, const void* p, int rank, const cuuint64_t* dims, const cuuint64_t* strides,
                const cuuint32_t* box, CUtensorMapSwizzle swz, CUtensorMapL2promotion promo) {
  cuuint32_t es[4] = {1, 1, 1, 1};
  fn(m, CU_TENSOR_MAP_DATA_TYPE_BFLOAT16, rank, (void*)p, dims, strides, box, es, CU_TENSOR_MAP_INTERLEAVE_NONE, swz, promo,
     CU_TENSOR_MAP_FLOAT_OOB_FILL_NONE);
}

extern "C" void kernel_launch(void* const* d_in, const int* in_sizes, int n_in, void* d_out, int out_size) {
  void* fp = nullptr;
  cudaDriverEntryPointQueryResult qr;
  cudaGetDriverEntryPoint("cuTensorMapEncodeTiled", &fp, cudaEnableDefault, &qr);
  EncodeFn fn = (EncodeFn)fp;
  Params P;
  P.shift_k = (const __nv_bfloat16*)d_in[3]; P.h = (const __nv_bfloat16*)d_in[4]; P.D = (const __nv_bfloat16*)d_in[5];
  P.q = (const __nv_bfloat16*)d_in[0];
  cudaGetSymbolAddress((void**)&P.part, g_part); cudaGetSymbolAddress((void**)&P.kv, g_kv); cudaGetSymbolAddress((void**)&P.o, g_o);
  cudaGetSymbolAddress((void**)&P.ocnt, g_ocnt); cudaGetSymbolAddress((void**)&P.epoch, g_epoch);
  cudaGetSymbolAddress((void**)&P.thr, c_thr); cudaGetSymbolAddress((void**)&P.img, c_img);
  P.x = (const __nv_bfloat16*)d_in[6]; P.w = (const __nv_bfloat16*)d_in[7]; P.wo = (const __nv_bfloat16*)d_in[8];
  const CUtensorMapSwizzle S128 = CU_TENSOR_MAP_SWIZZLE_128B, S32 = CU_TENSOR_MAP_SWIZZLE_32B;
  const CUtensorMapL2promotion P0 = CU_TENSOR_MAP_L2_PROMOTION_NONE, P128 = CU_TENSOR_MAP_L2_PROMOTION_L2_128B;
  { cuuint64_t d[2] = {1024, 2048}, s[1] = {2048}; cuuint32_t b[2] = {64, 128}; enc(fn, &P.tmX, d_in[6], 2, d, s, b, S128, P128); }
  { cuuint64_t d[3] = {1024, 1024, 3}, s[2] = {6144, 2048}; cuuint32_t b[3] = {64, 64, 3}; enc(fn, &P.tmW, d_in[7], 3, d, s, b, S128, P128); }
  { cuuint64_t d[4] = {64, 64, 16, 16}, s[3] = {2048, 131072, 128}; cuuint32_t b[4] = {64, 32, 2, 2}; enc(fn, &P.tmWo, d_in[8], 4, d, s, b, S128, P128); }
  { cuuint64_t d[4] = {64, 64, 16, 16}, s[3] = {2048, 131072, 128}; cuuint32_t b[4] = {64, 32, 2, 1}; enc(fn, &P.tmWo1, d_in[8], 4, d, s, b, S128, P128); }
  { cuuint64_t d[2] = {1024, 2048}, s[1] = {2048}; cuuint32_t b[2] = {16, 72}; enc(fn, &P.tmK, d_in[1], 2, d, s, b, S32, PKV); }
  { cuuint64_t d[2] = {1024, 2048}, s[1] = {2048}; cuuint32_t b[2] = {16, 64}; enc(fn, &P.tmV, d_in[2], 2, d, s, b, S32, PKV); }
  { cuuint64_t d[3] = {1024, 128, 16}, s[2] = {32768, 2048}; cuuint32_t b[3] = {16, 32, 2}; enc(fn, &P.tmQ, d_in[0], 3, d, s, b, S32, PKV); }
  { cuuint64_t d[3] = {1024, 128, 16}, s[2] = {65536, 4096}; cuuint32_t b[3] = {16, 32, 2}; enc(fn, &P.tmOA, d_out, 3, d, s, b, S32, P0); }
  { cuuint64_t d[2] = {2048, 2048}, s[1] = {4096}; cuuint32_t b[2] = {64, 64}; enc(fn, &P.tmOB, d_out, 2, d, s, b, S128, P0); }
  cudaFuncSetAttribute(fused_kernel, cudaFuncAttributeMaxDynamicSharedMemorySize, SMEM_TOTAL);
  fused_kernel<<<128, 384, SMEM_TOTAL>>>(P);
}
```

```cpp
#include <cuda_runtime.h>
#include <cuda_bf16.h>
#include <cuda_fp16.h>
#include <cuda.h>
#include <stdint.h>

template<int TA, int TB, int SA=1> __device__ __forceinline__ void wgmma_ss_n192(float (&d)[96], uint64_t da, uint64_t db, int scale_d) {
  asm volatile("{\n.reg .pred p;\nsetp.ne.b32 p, %98, 0;\n"
    "wgmma.mma_async.sync.aligned.m64n192k16.f32.bf16.bf16 {%0, %1, %2, %3, %4, %5, %6, %7, %8, %9, %10, %11, %12, %13, %14, %15, %16, %17, %18, %19, %20, %21, %22, %23, %24, %25, %26, %27, %28, %29, %30, %31, %32, %33, %34, %35, %36, %37, %38, %39, %40, %41, %42, %43, %44, %45, %46, %47, %48, %49, %50, %51, %52, %53, %54, %55, %56, %57, %58, %59, %60, %61, %62, %63, %64, %65, %66, %67, %68, %69, %70, %71, %72, %73, %74, %75, %76, %77, %78, %79, %80, %81, %82, %83, %84, %85, %86, %87, %88, %89, %90, %91, %92, %93, %94, %95}, %96, %97, p, %101, 1, %99, %100;\n}\n"
    : "+f"(d[0]), "+f"(d[1]), "+f"(d[2]), "+f"(d[3]), "+f"(d[4]), "+f"(d[5]), "+f"(d[6]), "+f"(d[7]), "+f"(d[8]), "+f"(d[9]), "+f"(d[10]), "+f"(d[11]), "+f"(d[12]), "+f"(d[13]), "+f"(d[14]), "+f"(d[15]), "+f"(d[16]), "+f"(d[17]), "+f"(d[18]), "+f"(d[19]), "+f"(d[20]), "+f"(d[21]), "+f"(d[22]), "+f"(d[23]), "+f"(d[24]), "+f"(d[25]), "+f"(d[26]), "+f"(d[27]), "+f"(d[28]), "+f"(d[29]), "+f"(d[30]), "+f"(d[31]), "+f"(d[32]), "+f"(d[33]), "+f"(d[34]), "+f"(d[35]), "+f"(d[36]), "+f"(d[37]), "+f"(d[38]), "+f"(d[39]), "+f"(d[40]), "+f"(d[41]), "+f"(d[42]), "+f"(d[43]), "+f"(d[44]), "+f"(d[45]), "+f"(d[46]), "+f"(d[47]), "+f"(d[48]), "+f"(d[49]), "+f"(d[50]), "+f"(d[51]), "+f"(d[52]), "+f"(d[53]), "+f"(d[54]), "+f"(d[55]), "+f"(d[56]), "+f"(d[57]), "+f"(d[58]), "+f"(d[59]), "+f"(d[60]), "+f"(d[61]), "+f"(d[62]), "+f"(d[63]), "+f"(d[64]), "+f"(d[65]), "+f"(d[66]), "+f"(d[67]), "+f"(d[68]), "+f"(d[69]), "+f"(d[70]), "+f"(d[71]), "+f"(d[72]), "+f"(d[73]), "+f"(d[74]), "+f"(d[75]), "+f"(d[76]), "+f"(d[77]), "+f"(d[78]), "+f"(d[79]), "+f"(d[80]), "+f"(d[81]), "+f"(d[82]), "+f"(d[83]), "+f"(d[84]), "+f"(d[85]), "+f"(d[86]), "+f"(d[87]), "+f"(d[88]), "+f"(d[89]), "+f"(d[90]), "+f"(d[91]), "+f"(d[92]), "+f"(d[93]), "+f"(d[94]), "+f"(d[95])
    : "l"(da), "l"(db), "r"(scale_d), "n"(TA), "n"(TB), "n"(SA));
}
template<int TA, int TB, int SA=1> __device__ __forceinline__ void wgmma_ss_n128(float (&d)[64], uint64_t da, uint64_t db, int scale_d) {
  asm volatile("{\n.reg .pred p;\nsetp.ne.b32 p, %66, 0;\n"
    "wgmma.mma_async.sync.aligned.m64n128k16.f32.bf16.bf16 {%0, %1, %2, %3, %4, %5, %6, %7, %8, %9, %10, %11, %12, %13, %14, %15, %16, %17, %18, %19, %20, %21, %22, %23, %24, %25, %26, %27, %28, %29, %30, %31, %32, %33, %34, %35, %36, %37, %38, %39, %40, %41, %42, %43, %44, %45, %46, %47, %48, %49, %50, %51, %52, %53, %54, %55, %56, %57, %58, %59, %60, %61, %62, %63}, %64, %65, p, %69, 1, %67, %68;\n}\n"
    : "+f"(d[0]), "+f"(d[1]), "+f"(d[2]), "+f"(d[3]), "+f"(d[4]), "+f"(d[5]), "+f"(d[6]), "+f"(d[7]), "+f"(d[8]), "+f"(d[9]), "+f"(d[10]), "+f"(d[11]), "+f"(d[12]), "+f"(d[13]), "+f"(d[14]), "+f"(d[15]), "+f"(d[16]), "+f"(d[17]), "+f"(d[18]), "+f"(d[19]), "+f"(d[20]), "+f"(d[21]), "+f"(d[22]), "+f"(d[23]), "+f"(d[24]), "+f"(d[25]), "+f"(d[26]), "+f"(d[27]), "+f"(d[28]), "+f"(d[29]), "+f"(d[30]), "+f"(d[31]), "+f"(d[32]), "+f"(d[33]), "+f"(d[34]), "+f"(d[35]), "+f"(d[36]), "+f"(d[37]), "+f"(d[38]), "+f"(d[39]), "+f"(d[40]), "+f"(d[41]), "+f"(d[42]), "+f"(d[43]), "+f"(d[44]), "+f"(d[45]), "+f"(d[46]), "+f"(d[47]), "+f"(d[48]), "+f"(d[49]), "+f"(d[50]), "+f"(d[51]), "+f"(d[52]), "+f"(d[53]), "+f"(d[54]), "+f"(d[55]), "+f"(d[56]), "+f"(d[57]), "+f"(d[58]), "+f"(d[59]), "+f"(d[60]), "+f"(d[61]), "+f"(d[62]), "+f"(d[63])
    : "l"(da), "l"(db), "r"(scale_d), "n"(TA), "n"(TB), "n"(SA));
}
template<int TA, int TB, int SA=1> __device__ __forceinline__ void wgmma_ss_n72(float (&d)[36], uint64_t da, uint64_t db, int scale_d) {
  asm volatile("{\n.reg .pred p;\nsetp.ne.b32 p, %38, 0;\n"
    "wgmma.mma_async.sync.aligned.m64n72k16.f32.bf16.bf16 {%0, %1, %2, %3, %4, %5, %6, %7, %8, %9, %10, %11, %12, %13, %14, %15, %16, %17, %18, %19, %20, %21, %22, %23, %24, %25, %26, %27, %28, %29, %30, %31, %32, %33, %34, %35}, %36, %37, p, %41, 1, %39, %40;\n}\n"
    : "+f"(d[0]), "+f"(d[1]), "+f"(d[2]), "+f"(d[3]), "+f"(d[4]), "+f"(d[5]), "+f"(d[6]), "+f"(d[7]), "+f"(d[8]), "+f"(d[9]), "+f"(d[10]), "+f"(d[11]), "+f"(d[12]), "+f"(d[13]), "+f"(d[14]), "+f"(d[15]), "+f"(d[16]), "+f"(d[17]), "+f"(d[18]), "+f"(d[19]), "+f"(d[20]), "+f"(d[21]), "+f"(d[22]), "+f"(d[23]), "+f"(d[24]), "+f"(d[25]), "+f"(d[26]), "+f"(d[27]), "+f"(d[28]), "+f"(d[29]), "+f"(d[30]), "+f"(d[31]), "+f"(d[32]), "+f"(d[33]), "+f"(d[34]), "+f"(d[35])
    : "l"(da), "l"(db), "r"(scale_d), "n"(TA), "n"(TB), "n"(SA));
}
template<int TB, int SA=1> __device__ __forceinline__ void wgmma_rs_n40(float (&d)[20], uint32_t a0, uint32_t a1, uint32_t a2, uint32_t a3, uint64_t db, int scale_d) {
  asm volatile("{\n.reg .pred p;\nsetp.ne.b32 p, %25, 0;\n"
    "wgmma.mma_async.sync.aligned.m64n40k16.f32.bf16.bf16 {%0, %1, %2, %3, %4, %5, %6, %7, %8, %9, %10, %11, %12, %13, %14, %15, %16, %17, %18, %19}, {%20, %21, %22, %23}, %24, p, %27, 1, %26;\n}\n"
    : "+f"(d[0]), "+f"(d[1]), "+f"(d[2]), "+f"(d[3]), "+f"(d[4]), "+f"(d[5]), "+f"(d[6]), "+f"(d[7]), "+f"(d[8]), "+f"(d[9]), "+f"(d[10]), "+f"(d[11]), "+f"(d[12]), "+f"(d[13]), "+f"(d[14]), "+f"(d[15]), "+f"(d[16]), "+f"(d[17]), "+f"(d[18]), "+f"(d[19])
    : "r"(a0), "r"(a1), "r"(a2), "r"(a3), "l"(db), "r"(scale_d), "n"(TB), "n"(SA));
}
template<int TB> __device__ __forceinline__ void wgmma_hrs_n64(uint32_t (&d)[16], uint32_t a0, uint32_t a1, uint32_t a2, uint32_t a3, uint64_t db, int scale_d) {
  asm volatile("{\n.reg .pred p;\nsetp.ne.b32 p, %21, 0;\n"
    "wgmma.mma_async.sync.aligned.m64n64k16.f16.f16.f16 {%0, %1, %2, %3, %4, %5, %6, %7, %8, %9, %10, %11, %12, %13, %14, %15}, {%16, %17, %18, %19}, %20, p, 1, 1, %22;\n}\n"
    : "+r"(d[0]), "+r"(d[1]), "+r"(d[2]), "+r"(d[3]), "+r"(d[4]), "+r"(d[5]), "+r"(d[6]), "+r"(d[7]), "+r"(d[8]), "+r"(d[9]), "+r"(d[10]), "+r"(d[11]), "+r"(d[12]), "+r"(d[13]), "+r"(d[14]), "+r"(d[15])
    : "r"(a0), "r"(a1), "r"(a2), "r"(a3), "l"(db), "r"(scale_d), "n"(TB));
}
template<int TB> __device__ __forceinline__ void wgmma_hrs_n32(uint32_t (&d)[8], uint32_t a0, uint32_t a1, uint32_t a2, uint32_t a3, uint64_t db, int scale_d) {
  asm volatile("{\n.reg .pred p;\nsetp.ne.b32 p, %13, 0;\n"
    "wgmma.mma_async.sync.aligned.m64n32k16.f16.f16.f16 {%0, %1, %2, %3, %4, %5, %6, %7}, {%8, %9, %10, %11}, %12, p, 1, 1, %14;\n}\n"
    : "+r"(d[0]), "+r"(d[1]), "+r"(d[2]), "+r"(d[3]), "+r"(d[4]), "+r"(d[5]), "+r"(d[6]), "+r"(d[7])
    : "r"(a0), "r"(a1), "r"(a2), "r"(a3), "l"(db), "r"(scale_d), "n"(TB));
}

__device__ __align__(128) const uint32_t c_thr[1536] = {
  0x33fb33ff,0xa49c9de4,0x33273352,0xaf2cae76,0x33e233f1,0xa96ca7bd,0x32c432f7,0xb045afdd,0x33b733cf,0xac3eaaf7,0x3250328c,0xb0eab099,
  0x3378339a,0xadbcacff,0x31cd3211,0xb182b137,0x33d033fb,0xaadea46a,0x299e2d17,0xb3e0b396,0x32fb337a,0xafd2adb1,0xa78b1f76,0xb3f2b3ff,
  0x318b3254,0xb1c5b0e5,0xae6bac32,0xb354b3b8,0x2f4230a3,0xb321b285,0xb133b040,0xb215b2c7,0x337c33f2,0xada5a759,0xb179afc8,0xb1d6b2fe,
  0x31463293,0xb204b08e,0xb394b2ba,0xad23b055,0x2b402f4e,0xb3cbb31e,0xb3e4b3f9,0x293ba533,0xac269c52,0xb3bab400,0xb258b357,0x30e02e5f,
  0x330133e5,0xafbda922,0xb3f3b3c9,0x2727ab59,0x2deb314a,0xb36fb200,0xb194b32f,0x31bc2f0a,0xacdb2084,0xb39fb3ff,0xa565aea4,0x33f93347,
  0xb2b6b0db,0xb05ab25c,0x30892c1a,0x329733bc,0x326033d4,0xb0d6aa94,0xb00ab29b,0x32e83084,0x20e82f64,0xb3feb318,0x2d8da597,0x338133f8,
  0xb1fcae48,0xb14fb35c,0x339031b8,0x2d3a3199,0xb3e6b3ae,0x2909ac7b,0x32d133f4,0xb030a6f5,0x319d33bf,0xb1b3ac02,0x2e3ca874,0x335e33ec,
  0xacc32b89,0xb3a3b3c6,0x33f83276,0x25c930b7,0xb3dcb1f8,0xaa01b154,0x30653335,0xb2b0aef4,0xb107b383,0x32392d81,0xafa6214d,0xb307b3fe,
  0x30bc33a5,0xb273acb7,0x33c5311b,0x2ba23229,0xb0cc94b6,0xb267b400,0x30153360,0xb2e1ae31,0xb385b3ab,0x2d76ac93,0xb166a691,0xb1e7b3f5,
  0x22deb06a,0x33fd32ac,0xb337b3da,0x2ee8aa19,0x2f853387,0xb310ad6a,0x322d33fe,0xb1162216,0xb2a9abd3,0xb06fb3c2,0xb07428a6,0xb2a5b3ea,
  0xb111b3e9,0x323128be,0xb30db3c3,0x2f90abba,0x31aa227a,0x31a633fd,0x2e25ad5e,0x33633389,0x2d6a3365,0xb387ae1a,0xa21631aa,0xb3feb1a6,
  0xb3c2af85,0xabd3b310,0xb3eab22d,0x28a6b116,0xa8beb2a9,0x33e9306f,0x2bbab074,0x33c332a5,0x33fd3111,0x227a3231,0x3389330d,0xad5e2f90,
  0x2a63333f,0xb3d7aec6,0xb2a2a1b1,0xb07ab3fe,0xb3f7b158,0x25fbb1f4,0xacb7b38b,0x33a52d52,0x2e0eb025,0x336832d8,0x340030bc,0x14b63273,
  0x323533c0,0xb10c2beb,0xac9330cc,0xb3abb267,0x23433316,0xb3fdaf6f,0xb38eb225,0x2d46b11f,0xb342b29e,0x2ebbb07f,0x31e3aa7c,0x316b33d6,
  0x3264a6c3,0x30d133f5,0x2c0233ac,0xb3bfac87,0x28f0336a,0xb3e7ae02,0xb3c6b19d,0x2b89b1b3,0xa59732e8,0xb3f8b00a,0xaccfb3ed,0x33a1285b,
  0xb1b8b381,0x3199ad8d,0x336c31df,0xadf73170,0x33f42d3a,0x26f53390,0xb30423a7,0xafb2b3fc,0xb05f3030,0xb2b3b2d1,0x29e8b27a,0x33dd30b2,
  0xab5932b6,0xb3c9b05a,0x30adb089,0x327e3297,0xaf0ab3f3,0x332fa727,0x240633b0,0xb3fcac6f,0x33473194,0xaea431bc,0xb174b359,0x31daae54,
  0xb3bca565,0xac1ab3f9,0x33ee2f59,0xa842331b,0xaddf3281,0xb371b0a8,0x34002b40,0x1c5233cb,0xa759b3ef,0x33f22829,0xb2fe2c26,0xafc8b3ba,
  0x308e337c,0xb2932da5,0x3055b179,0x32ba31d6,0xb31eb146,0x2f4eb204,0xa5333394,0xb3f9ad23,0xaff33249,0xb2f1b0f3,0x30e532fb,0xb2542fd2,
  0x2b28b373,0x33cc2dd4,0xb285b18b,0x30a3b1c5,0x246a33fa,0xb3fba500,0x33962f42,0xad173321,0xadb1b3d0,0x337aaade,0xb3ffa99e,0x1f76b3e0,
  0xb0ee320d,0xb24db13c,0xac4b3398,0xb3b5ad0b,0x304ab289,0x32c1309e,0x2985b3ce,0x33e12b0f,0xaf3732f4,0xb324afe8,0xa4ce33f0,0xb3faa7ef,
  0x2dc8b34f,0x33762e82,0x9de4b3ff,0x33ff1ead,0xb1c931cd,0xb186b182,0xb3762e82,0xadc8b34f,0x324db13c,0x30ee320d,0x33b5ad0b,0x2c4b3398,
  0xb2c1309e,0xb04ab289,0xb3e12b0f,0xa985b3ce,0x3324afe8,0x2f3732f4,0x33faa7ef,0x24ce33f0,0xb285318b,0xb0a3b1c5,0xb2c7ae6b,0x3040b354,
  0x3396af42,0x2d173321,0x31413133,0xb2093215,0xb3ff299e,0x9f76b3e0,0xae8db2bd,0x334cb050,0x33b8278b,0xac3233f2,0x281033b3,0xb3ef2c57,
  0xb31e3146,0xaf4eb204,0xa533b394,0x33f9ad23,0x3400ab40,0x9c5233cb,0xae5f33e4,0xb357a93b,0xb2feac26,0x2fc8b3ba,0x3245b258,0x30f830e0,
  0x30553179,0xb2ba31d6,0xb3df2e99,0xa9b6b34a,0xb39230fd,0xad2fb241,0x3200b301,0x314a2fbd,0x337f1b11,0xad993400,0xb3ff2deb,0xa084b36f,
  0xb005b129,0x32ebb21d,0x325c2cdb,0xb0db339f,0xa92233de,0xb3e529cf,0xab59b2b6,0x33c9b05a,0xb3dd30b2,0xa9e8b27a,0x33d4ab71,0xaa9433c8,
  0x32212c0e,0xb12433bd,0xaf64b0d6,0x3318b260,0x197fb345,0x3400aeaf,0xae4833fe,0xb35c20e8,0xb23d3332,0xb102aeff,0x33aeb14f,0x2c7b31fc,
  0xb3fe3065,0xa14db2b0,0x2ebb307f,0xb342329e,0x300f2fa6,0xb2e53307,0x30d1b3f5,0x326426c3,0x302ab400,0x32d517db,0xb3e72e02,0x28f0b36a,
  0xb3fd2f6f,0x2343b316,0x2d46311f,0xb38e3225,0xb3f53015,0x2691b2e1,0xaf9b33eb,0xb30a288d,0x2a193166,0xb3da31e7,0x33d7aec6,0xaa63333f,
  0x3313b337,0x2f7a2ee8,0xa5fbb1f4,0x33f7b158,0xb1a1a8d7,0x31afb3e8,0xb36832d8,0xae0eb025,0xb3c22f85,0x2bd3b310,0xb3ea322d,0xa8a6b116,
  0xa8be32a9,0xb3e9306f,0x2bba3074,0xb3c332a5,0x33fdb111,0xa27a3231,0x3389b30d,0x2d5e2f90,0xa216b1aa,0x33feb1a6,0xaed2ae25,0x333db363,
  0xb3652edd,0x2e1ab33a,0xb1aa227a,0x31a6b3fd,0xaf853387,0xb3102d6a,0xb22d33fe,0xb116a216,0x32a9abd3,0xb06f33c2,0x307428a6,0xb2a533ea,
  0x3111b3e9,0x3231a8be,0x330db3c3,0x2f902bba,0xb2e12e31,0x3015b360,0x288db1a1,0x33ebb1af,0xb1e733f5,0xb1662691,0xb33f2f9b,0x2ec6b30a,
  0x2ee82a19,0xb33733da,0xb15833d7,0xb1f42a63,0x33e8b313,0x28d72f7a,0x302525fb,0xb2d833f7,0xb2392d81,0x3107b383,0x3307b3fe,0x2fa6214d,
  0xb35e33ec,0xae3ca874,0x97dbb00f,0x3400b2e5,0xa5c930b7,0xb3f83276,0xb316302a,0x2f6fb2d5,0x32b0aef4,0xb0653335,0xb29e33fd,0xb07f2343,
  0xb1702ccf,0x31dfb3a1,0x3345b124,0xaeaf3221,0xb3fc336c,0xa3a7adf7,0x3332b400,0x2eff997f,0xb0b23304,0xb27a2fb2,0x2b71b102,0x33c8b23d,
  0x2c0e29e8,0xb3bd33dd,0xb0d62a94,0x3260b3d4,0xb0892c1a,0x3297b3bc,0x2aad2842,0xb3d333ee,0xb3b0327e,0x2c6fb0ad,0x3241b035,0xb0fd32ce,
  0xb35933fc,0xae542406,0x3400b392,0x1b112d2f,0xaf5931da,0xb31b3174,0x321db37f,0x3129ad99,0xaf152ac6,0x332cb3d2,0xb1463293,0xb204308e,
  0xb281312e,0x30a8b219,0xab402f4e,0xb3cb331e,0xb3ef3371,0x2829addf,0x2c269c52,0xb3ba3400,0xb37c33f2,0xada52759,0x3179afc8,0xb1d632fe,
  0xacf32953,0x339cb3e3,0xb3fa33cc,0x2500ab28,0xb0942f21,0x3290b32a,0xb3d033fb,0xaade246a,0xb249317d,0x30f3b1d2,0xb2fb337a,0xafd22db1,
  0xb37332f1,0x2dd4aff3,0xb18b3254,0xb1c530e5,0xa96c27bd,0x33e2b3f1,0xb0452fdd,0x32c4b2f7,0xac3e2af7,0x33b7b3cf,0xb0ea3099,0x3250b28c,
  0xadbc2cff,0x3378b39a,0xb1823137,0x31cdb211,0xaf2c2e76,0x3327b352,0xb20d31c9,0x313cb186,0x313c3186,0xb20db1c9,0x2d0b2dc8,0xb398b376,
  0x309e30ee,0xb289b24d,0x2b0f2c4b,0xb3ceb3b5,0x2fe8304a,0xb2f4b2c1,0x27ef2985,0xb3f0b3e1,0x2e822f37,0xb34fb324,0x1ead24ce,0xb3ffb3fa,
  0xb2bdb209,0xb050b141,0xb290b32a,0x30942f21,0xb3b3b34c,0xac57ae8d,0xb0f3b1d2,0x3249317d,0xb400b3ef,0x1d1ba810,0xadd4aff3,0x337332f1,
  0xb39cb3e3,0x2cf32953,0xa500ab28,0x33fa33cc,0xae99b0f8,0x334a3245,0x33ff33b2,0x201f2c63,0x2438a9b6,0x33fc33df,0x332c33d2,0xaf15aac6,
  0x303a2ce7,0x32cb339e,0x30a83219,0xb281b12e,0x32ee31c0,0x2ffe3190,0x28292ddf,0xb3efb371,0x33b0327e,0x2c6f30ad,0xb241b035,0xb0fdb2ce,
  0x335933fc,0xae54a406,0xb400b392,0x1b11ad2f,0x2f5931da,0xb31bb174,0xb21db37f,0x31292d99,0xaaad2842,0xb3d3b3ee,0xa9cfb005,0x33de32eb,
  0x285b305f,0xb3edb2b3,0x2c0ea9e8,0x33bd33dd,0xb170accf,0xb1dfb3a1,0x33453124,0x2eaf3221,0xb3fcb36c,0x23a7adf7,0x33323400,0xaeff997f,
  0xb0b2b304,0x327a2fb2,0x2b713102,0xb3c8b23d,0xb400b2e5,0x17dbb00f,0x2e023264,0xb36ab0d1,0xaf6fb2d5,0x3316302a,0xb11fa8f0,0xb225b3e7,
  0x307f2343,0x329e33fd,0xb3d6b38e,0x2a7cad46,0x33f53342,0xa6c32ebb,0xac87b1e3,0x33ac316b,0x28d7af7a,0x33e83313,0xb2d8b3f7,0x3025a5fb,
  0x33eb31af,0x288d31a1,0x2bebae0e,0x33c03368,0x2ec6330a,0xb33faf9b,0x33fe3235,0x21b1310c,0xb1f4aa63,0xb158b3d7,0x2d5232a2,0xb38bb07a,
  0x33a7333d,0xacab2ed2,0x33f63162,0x262d31eb,0xaa4b301a,0xb3d8b2de,0x2a32326b,0xb3d9b0c7,0xb3f6b26f,0x265fb0c1,0xb3a9b020,0xac9fb2db,
  0x0e48b15d,0x340031f0,0xae1ab33a,0x33652edd,0xaed22e25,0xb33db363,0xb1eb0e48,0xb162b400,0xb2deb3a7,0x301aacab,0xb0c7b3f6,0x326b262d,
  0x30c1aa4b,0x326f33d8,0x32db2a32,0x302033d9,0x31f033f6,0xb15d265f,0x2edd33a9,0xb33aac9f,0xb2acb385,0x306aad76,0x2a19b166,0x33da31e7,
  0x3229a2de,0x311b33fd,0x33133337,0xaf7a2ee8,0x2e3133c5,0xb360aba2,0xb1a128d7,0xb1afb3e8,0xb3f5b015,0xa691b2e1,0xaf9bb3eb,0x330a288d,
  0x3154acc3,0x31f833a3,0x2ef433f8,0xb335a5c9,0x2d8133dc,0xb383aa01,0xb3feb065,0x214db2b0,0xb3ecb107,0x2874b239,0x300fafa6,0x32e53307,
  0x30b7ae3c,0x3276335e,0x302a3400,0xb2d517db,0x312433bd,0xb2212c0e,0xb318b260,0x2f64b0d6,0xb400aeaf,0x997fb345,0x335c20e8,0x2e4833fe,
  0x3102aeff,0x323d3332,0xac7b31fc,0xb3aeb14f,0x2a9433c8,0xb3d4ab71,0xb084b3e6,0x329ba909,0xb2ce2aad,0xb035b3d3,0x33e529cf,0x292233de,
  0x2d2fb241,0x339230fd,0xb14a2fbd,0xb200b301,0x2d993400,0xb37f1b11,0x2084b36f,0x33ff2deb,0xb2ebb21d,0x3005b129,0x30db339f,0xb25c2cdb,
  0xae5fb3e4,0x3357a93b,0xb190303a,0xb1c0b2cb,0x32453258,0xb0f830e0,0x2c63b2ee,0x33b22ffe,0xb3dfae99,0x29b6b34a,0x2ac633ff,0xb3d2a01f,
  0x339ea438,0x2ce733fc,0xb12eb32c,0x3219af15,0x33b8a78b,0x2c3233f2,0x2810b3b3,0x33ef2c57,0xb2c72e6b,0xb040b354,0x29533400,0xb3e31d1b,
  0x3141b133,0x32093215,0xaf21b39c,0x332aacf3,0xae8d32bd,0xb34cb050,0x317d3290,0xb1d23094,0x27bd33fb,0xb3f1249c,0x2fdd3327,0xb2f72f2c,
  0xaaf7b3e2,0x33cfa96c,0xb099b2c4,0x328cb045,0x2cff33b7,0xb39a2c3e,0x31373250,0xb21130ea,0xae76b378,0x3352adbc,0xb1c9b1cd,0x3186b182,
  0xb3ff1ead,0x1de4b3ff,0xb352adbc,0x2e76b378,0x33f1249c,0xa7bd33fb,0x32f72f2c,0xafdd3327,0xb3cfa96c,0x2af7b3e2,0xb28cb045,0x3099b2c4,
  0x339a2c3e,0xacff33b7,0x321130ea,0xb1373250,0x2953b400,0x33e31d1b,0x33ccadd4,0x2b283373,0xaf21339c,0xb32aacf3,0xb3fb2500,0x246ab3fa,
  0x317db290,0x31d23094,0x337a2ade,0xadb133d0,0xb2f130f3,0xaff3b249,0xb254afd2,0x30e5b2fb,0x339e2438,0xace733fc,0xb12e332c,0xb219af15,
  0xb190b03a,0x31c0b2cb,0x3371b0a8,0x2ddf3281,0x2c6332ee,0xb3b22ffe,0xb3f22829,0x2759b3ef,0x2ac6b3ff,0x33d2a01f,0x32932da5,0xb08e337c,
  0xaf0a33f3,0xb32fa727,0x2406b3b0,0x33fcac6f,0x3347b194,0x2ea431bc,0xb1743359,0xb1daae54,0xb3bc2565,0x2c1ab3f9,0x33eeaf59,0x2842331b,
  0x30ad3089,0xb27e3297,0xb2ceaaad,0x3035b3d3,0xb29ba909,0x3084b3e6,0x305f3030,0xb2b332d1,0x259732e8,0xb3f8300a,0x2ccfb3ed,0x33a1a85b,
  0x31b8b381,0x31992d8d,0xb36c31df,0xadf7b170,0xb3f42d3a,0x26f5b390,0x330423a7,0xafb233fc,0x316bb3d6,0x31e32a7c,0xb3832a01,0x2d81b3dc,
  0xb3bf2c87,0x2c02b3ac,0x28743239,0xb3ec3107,0x2b8931b3,0xb3c6319d,0x3276b35e,0x30b72e3c,0x31f8b3a3,0x31542cc3,0xb33525c9,0x2ef4b3f8,
  0x310c2beb,0xb23533c0,0x33abb267,0x2c9330cc,0x307ab3fe,0x32a2a1b1,0xb06aad76,0x32acb385,0xb3a52d52,0x2cb7b38b,0xb11b33fd,0xb229a2de,
  0x94b63273,0xb40030bc,0x3360aba2,0xae3133c5,0xb2de33a7,0xb01aacab,0xb0c733f6,0xb26b262d,0x30c12a4b,0xb26f33d8,0x32dbaa32,0xb02033d9,
  0x31f0b3f6,0x315d265f,0x2eddb3a9,0x333aac9f,0xb1eb8e48,0x3162b400,0xb3872e1a,0x2d6ab365,0xae25ad5e,0x3363b389,0x8e48b15d,0x3400b1f0,
  0xb3a7333d,0xacabaed2,0xb3f63162,0x262db1eb,0x2a4b301a,0xb3d832de,0xaa32326b,0xb3d930c7,0x33f6b26f,0x265f30c1,0x33a9b020,0xac9f32db,
  0x33c0b368,0x2beb2e0e,0x30cc94b6,0xb2673400,0x21b1b10c,0x33feb235,0x3385b3ab,0x2d762c93,0xb38b307a,0x2d52b2a2,0xa2deb06a,0x33fdb2ac,
  0xb0bc33a5,0xb2732cb7,0xb3c5311b,0x2ba2b229,0x26c32ebb,0xb3f53342,0xb3ac316b,0x2c87b1e3,0x336ab0d1,0xae023264,0xb19d33bf,0xb1b32c02,
  0x3225b3e7,0x311fa8f0,0x2cc32b89,0xb3a333c6,0xaa7cad46,0x33d6b38e,0x33dcb1f8,0xaa013154,0xb3fe3318,0x20e8af64,0x3381b3f8,0x2d8d2597,
  0xb14f335c,0xb1fc2e48,0x2d3ab199,0x3390b1b8,0x29092c7b,0xb3e633ae,0xb03026f5,0x32d1b3f4,0x32e8b084,0xb00a329b,0xb3ed32b3,0x285bb05f,
  0x29cfb005,0x33deb2eb,0xb05a325c,0xb2b630db,0xafbd2922,0x3301b3e5,0x27272b59,0xb3f333c9,0xb36f3200,0x2debb14a,0x31bcaf0a,0xb194332f,
  0xb39f33ff,0xacdba084,0x33f9b347,0xa5652ea4,0x3394b2ba,0xad233055,0xa438a9b6,0x33fcb3df,0x33e4b3f9,0x293b2533,0xb03a2ce7,0x32cbb39e,
  0x3258b357,0x30e0ae5f,0xb2ee31c0,0x2ffeb190,0x2e99b0f8,0x334ab245,0xb3ff33b2,0x201fac63,0xaf4230a3,0xb3213285,0x3133b040,0xb21532c7,
  0xa99e2d17,0xb3e03396,0x32bdb209,0xb0503141,0x278b1f76,0xb3f233ff,0x33b3b34c,0xac572e8d,0x2e6bac32,0xb35433b8,0x3400b3ef,0x1d1b2810,
  0xb289324d,0x309eb0ee,0xb3ce33b5,0x2b0fac4b,0xb2f432c1,0x2fe8b04a,0xb3f033e1,0x27efa985,0xb34f3324,0x2e82af37,0xb3ff33fa,0x1eada4ce,
  0xb3983376,0x2d0badc8,0xb3fb33ff,0xa49c1de4,0x351c35f6,0xac93a617,0xb8a3b93c,0x308d2a16,0x32f43448,0xb160afa5,0xb6a4b7fe,0x353a3389,
  0x2fa53160,0xb448b2f4,0xb389b53a,0x37fe36a4,0x26172c93,0xb5f6b51c,0xaa16b08d,0x393c38a3,0x34c3358c,0xac47a5b2,0xb85fb8f3,0x304229b1,
  0x327e33fd,0xb106af26,0xb63cb785,0x34e7330f,0x2f263106,0xb3fdb27e,0xb30fb4e7,0x3785363c,0x25b22c47,0xb58cb4c3,0xa9b1b042,0x38f3385f,
  0x346a3523,0xabf6a54d,0xb81ab8a8,0x2fef294d,0x3209336b,0xb0acaea7,0xb5d4b70a,0x34933294,0x2ea730ac,0xb36bb209,0xb294b493,0x370a35d4,
  0x254d2bf6,0xb523b46a,0xa94dafef,0x38a8381a,0x341334bc,0xab5fa4e9,0xb7a6b85a,0x2f5928e8,0x319432da,0xb052ae28,0xb56ab68d,0x343e3219,
  0x2e283052,0xb2dab194,0xb219b43e,0x368d356a,0x24e92b5f,0xb4bcb413,0xa8e8af59,0x385a37a6,0x33783456,0xaac8a484,0xb715b80a,0x2ec32884,
  0x3120324a,0xaff2ada9,0xb4ffb60e,0x33d3319e,0x2da92ff2,0xb24ab120,0xb19eb3d3,0x360e34ff,0x24842ac8,0xb456b378,0xa884aec3,0x380a3715,
  0x32cd33e3,0xaa31a420,0xb682b76f,0x2e2d281f,0x30ac31bb,0xaf3fad2a,0xb493b58d,0x33283122,0x2d2a2f3f,0xb1bbb0ac,0xb122b328,0x358d3493,
  0x24202a31,0xb3e3b2cd,0xa81fae2d,0x376f3682,0x3223331c,0xa999a376,0xb5ebb6c6,0x2d972776,0x3039312d,0xae8dacac,0xb426b50b,0x327c30a6,
  0x2cac2e8d,0xb12db039,0xb0a6b27c,0x350b3426,0x23762999,0xb31cb223,0xa776ad97,0x36c635eb,0x317a3257,0xa902a2ad,0xb552b61a,0x2d0026ad,
  0x2f8c309f,0xaddcac2e,0xb371b487,0x31cf3029,0x2c2e2ddc,0xb09faf8c,0xb029b1cf,0x34873371,0x22ad2902,0xb257b17a,0xa6adad00,0x361a3552,
  0x30d23194,0xa86ba1e4,0xb4b7b56a,0x2c6a25e4,0x2ea73012,0xad2aab5f,0xb294b402,0x31222f59,0x2b5f2d2a,0xb012aea7,0xaf59b122,0x34023294,
  0x21e4286b,0xb194b0d2,0xa5e4ac6a,0x356a34b7,0x302c30d2,0xa7a9a11b,0xb41ab4b7,0x2ba7251b,0x2dc22f0c,0xac79aa63,0xb1b6b2f7,0x30742e5f,
  0x2a632c79,0xaf0cadc2,0xae5fb074,0x32f731b6,0x211b27a9,0xb0d2b02c,0xa51baba7,0x34b7341a,0x2f0c3012,0xa67ba052,0xb2f7b402,0x2a7a2452,
  0x2cde2df5,0xab91a967,0xb0d7b1e8,0x2f8b2d65,0x29672b91,0xadf5acde,0xad65af8b,0x31e830d7,0x2052267b,0xb012af0c,0xa452aa7a,0x340232f7,
  0x2dc22ea7,0xa54d9f12,0xb1b6b294,0x294d2311,0x2bf62cde,0xaa31a86b,0xafefb0d7,0x2e2d2c6a,0x286b2a31,0xacdeabf6,0xac6aae2d,0x30d72fef,
  0x1f12254d,0xaea7adc2,0xa311a94d,0x329431b6,0x2c792d2a,0xa4209d7f,0xb074b122,0x281f217f,0x2a312b91,0xa8d0a6e0,0xae2daf8b,0x2cce2ade,
  0x26e028d0,0xab91aa31,0xaadeacce,0x2f8b2e2d,0x1d7f2420,0xad2aac79,0xa17fa81f,0x31223074,0x2a632b5f,0xa1e49bdb,0xae5faf59,0x25e41fdb,
  0x286b2967,0xa6e0a4e9,0xac6aad65,0x2ade28e8,0x24e926e0,0xa967a86b,0xa8e8aade,0x2d652c6a,0x1bdb21e4,0xab5faa63,0x9fdba5e4,0x2f592e5f,
  0x27a9286b,0x9f1298b6,0xaba7ac6a,0x23111cb6,0x254d267b,0xa420a1e4,0xa94daa7a,0x281f25e4,0x21e42420,0xa67ba54d,0xa5e4a81f,0x2a7a294d,
  0x18b61f12,0xa86ba7a9,0x9cb6a311,0x2c6a2ba7,0x211b21e4,0x98b69248,0xa51ba5e4,0x1cb61648,0x1f122052,0x9d7f9bdb,0xa311a452,0x217f1fdb,
  0x1bdb1d7f,0xa0529f12,0x9fdba17f,0x24522311,0x124818b6,0xa1e4a11b,0x96489cb6,0x25e4251b,0xa11ba1e4,0x18b61248,0x251b25e4,0x9cb69648,
  0x9f12a052,0x1d7f1bdb,0x23112452,0xa17f9fdb,0x9bdb9d7f,0x20521f12,0x1fdb217f,0xa452a311,0x924898b6,0x21e4211b,0x16481cb6,0xa5e4a51b,
  0xa7a9a86b,0x1f1218b6,0x2ba72c6a,0xa3119cb6,0xa54da67b,0x242021e4,0x294d2a7a,0xa81fa5e4,0xa1e4a420,0x267b254d,0x25e4281f,0xaa7aa94d,
  0x98b69f12,0x286b27a9,0x1cb62311,0xac6aaba7,0xaa63ab5f,0x21e41bdb,0x2e5f2f59,0xa5e49fdb,0xa86ba967,0x26e024e9,0x2c6a2d65,0xaadea8e8,
  0xa4e9a6e0,0x2967286b,0x28e82ade,0xad65ac6a,0x9bdba1e4,0x2b5f2a63,0x1fdb25e4,0xaf59ae5f,0xac79ad2a,0x24201d7f,0x30743122,0xa81fa17f,
  0xaa31ab91,0x28d026e0,0x2e2d2f8b,0xacceaade,0xa6e0a8d0,0x2b912a31,0x2ade2cce,0xaf8bae2d,0x9d7fa420,0x2d2a2c79,0x217f281f,0xb122b074,
  0xadc2aea7,0x254d1f12,0x31b63294,0xa94da311,0xabf6acde,0x2a31286b,0x2fef30d7,0xae2dac6a,0xa86baa31,0x2cde2bf6,0x2c6a2e2d,0xb0d7afef,
  0x9f12a54d,0x2ea72dc2,0x2311294d,0xb294b1b6,0xaf0cb012,0x267b2052,0x32f73402,0xaa7aa452,0xacdeadf5,0x2b912967,0x30d731e8,0xaf8bad65,
  0xa967ab91,0x2df52cde,0x2d652f8b,0xb1e8b0d7,0xa052a67b,0x30122f0c,0x24522a7a,0xb402b2f7,0xb02cb0d2,0x27a9211b,0x341a34b7,0xaba7a51b,
  0xadc2af0c,0x2c792a63,0x31b632f7,0xb074ae5f,0xaa63ac79,0x2f0c2dc2,0x2e5f3074,0xb2f7b1b6,0xa11ba7a9,0x30d2302c,0x251b2ba7,0xb4b7b41a,
  0xb0d2b194,0x286b21e4,0x34b7356a,0xac6aa5e4,0xaea7b012,0x2d2a2b5f,0x32943402,0xb122af59,0xab5fad2a,0x30122ea7,0x2f593122,0xb402b294,
  0xa1e4a86b,0x319430d2,0x25e42c6a,0xb56ab4b7,0xb17ab257,0x290222ad,0x3552361a,0xad00a6ad,0xaf8cb09f,0x2ddc2c2e,0x33713487,0xb1cfb029,
  0xac2eaddc,0x309f2f8c,0x302931cf,0xb487b371,0xa2ada902,0x3257317a,0x26ad2d00,0xb61ab552,0xb223b31c,0x29992376,0x35eb36c6,0xad97a776,
  0xb039b12d,0x2e8d2cac,0x3426350b,0xb27cb0a6,0xacacae8d,0x312d3039,0x30a6327c,0xb50bb426,0xa376a999,0x331c3223,0x27762d97,0xb6c6b5eb,
  0xb2cdb3e3,0x2a312420,0x3682376f,0xae2da81f,0xb0acb1bb,0x2f3f2d2a,0x3493358d,0xb328b122,0xad2aaf3f,0x31bb30ac,0x31223328,0xb58db493,
  0xa420aa31,0x33e332cd,0x281f2e2d,0xb76fb682,0xb378b456,0x2ac82484,0x3715380a,0xaec3a884,0xb120b24a,0x2ff22da9,0x34ff360e,0xb3d3b19e,
  0xada9aff2,0x324a3120,0x319e33d3,0xb60eb4ff,0xa484aac8,0x34563378,0x28842ec3,0xb80ab715,0xb413b4bc,0x2b5f24e9,0x37a6385a,0xaf59a8e8,
  0xb194b2da,0x30522e28,0x356a368d,0xb43eb219,0xae28b052,0x32da3194,0x3219343e,0xb68db56a,0xa4e9ab5f,0x34bc3413,0x28e82f59,0xb85ab7a6,
  0xb46ab523,0x2bf6254d,0x381a38a8,0xafefa94d,0xb209b36b,0x30ac2ea7,0x35d4370a,0xb493b294,0xaea7b0ac,0x336b3209,0x32943493,0xb70ab5d4,
  0xa54dabf6,0x3523346a,0x294d2fef,0xb8a8b81a,0xb4c3b58c,0x2c4725b2,0x385f38f3,0xb042a9b1,0xb27eb3fd,0x31062f26,0x363c3785,0xb4e7b30f,
  0xaf26b106,0x33fd327e,0x330f34e7,0xb785b63c,0xa5b2ac47,0x358c34c3,0x29b13042,0xb8f3b85f,0xb51cb5f6,0x2c932617,0x38a3393c,0xb08daa16,
  0xb2f4b448,0x31602fa5,0x36a437fe,0xb53ab389,0xafa5b160,0x344832f4,0x3389353a,0xb7feb6a4,0xa617ac93,0x35f6351c,0x2a16308d,0xb93cb8a3,
};
__device__ __align__(128) const uint32_t c_img[2560] = {
  0x326d31ed,0x333b32dd,0x33c33388,0x33fe33ea,0x33c331ed,0x31ed33c3,0xa8b22d64,0xb33bb0c4,0x33ea31ed,0xad64301d,0xb2ddb388,0x315fa8b2,
  0x32dd31ed,0xb3feabc6,0x326dad64,0xad64326d,0x30c431ed,0xaed7b2dd,0x2bc63388,0xa248b3ea,0x2bc631ed,0x315fb3c3,0xb3ea2d64,0x2ed730c4,
  0xa8b231ed,0x3388b01d,0x301db388,0xb1ed28b2,0xb01d31ed,0x22482bc6,0x30c4ad64,0x3388b26d,0x33ea33fe,0x338833c3,0x32dd333b,0x31ed326d,
  0xb2ddb3fe,0xa248b01d,0x326d2ed7,0x338833ea,0x30c433fe,0xb33babc6,0xabc6b33b,0x33fe30c4,0xabc6b3fe,0x31ed32dd,0xb3eaaed7,0x333ba8b2,
  0xa8b233fe,0x2d64b3c3,0xb01d333b,0x315fb26d,0x301db3fe,0xb3fe301d,0x30c42ed7,0x2d64b3ea,0xb26d33fe,0x2ed72bc6,0x33c3b33b,0xa248b0c4,
  0x33c3b3fe,0x315fb2dd,0x28b2aed7,0xaed728b2,0xb0c4b15f,0xaed7b01d,0xabc6ad64,0xa248a8b2,0xabc6b15f,0x315f2bc6,0x33ea3388,0x2ed7326d,
  0x28b2b15f,0x338832dd,0xb01d2d64,0xb1edb3ea,0x301db15f,0x224833c3,0xb0c4b388,0x338830c4,0x326db15f,0xb33b301d,0x33c3ad64,0xb3fe28b2,
  0x33c3b15f,0xb1edabc6,0xa8b23388,0x333bb26d,0x33eab15f,0x2d64b2dd,0xb2dd2d64,0xb15f33ea,0x32ddb15f,0x33feb3c3,0x326db388,0x2d64b0c4,
  0x28b22248,0x2d642bc6,0x301d2ed7,0x315f30c4,0xb01da248,0xb3feb2dd,0xb0c4b33b,0x2d64a8b2,0x326d2248,0x2ed733c3,0xb3c3aed7,0xa248b26d,
  0xb3c3a248,0x315fb01d,0xa8b2333b,0xaed7b3ea,0x33ea2248,0xb388abc6,0x32dd2ed7,0xb1edb0c4,0xb2dda248,0x224832dd,0x326db33b,0xb38828b2,
  0x30c42248,0x333bb3c3,0xabc6aed7,0xb3fe326d,0xabc6a248,0xb1ed301d,0xb3ea333b,0xb33b33ea,0xb26d31ed,0xb33b32dd,0xb3c33388,0xb3fe33ea,
  0xb3c331ed,0xb1ed33c3,0x28b22d64,0x333bb0c4,0xb3ea31ed,0x2d64301d,0x32ddb388,0xb15fa8b2,0xb2dd31ed,0x33feabc6,0xb26dad64,0x2d64326d,
  0xb0c431ed,0x2ed7b2dd,0xabc63388,0x2248b3ea,0xabc631ed,0xb15fb3c3,0x33ea2d64,0xaed730c4,0x28b231ed,0xb388b01d,0xb01db388,0x31ed28b2,
  0x301d31ed,0xa2482bc6,0xb0c4ad64,0xb388b26d,0xb3ea33fe,0xb38833c3,0xb2dd333b,0xb1ed326d,0x32ddb3fe,0x2248b01d,0xb26d2ed7,0xb38833ea,
  0xb0c433fe,0x333babc6,0x2bc6b33b,0xb3fe30c4,0x2bc6b3fe,0xb1ed32dd,0x33eaaed7,0xb33ba8b2,0x28b233fe,0xad64b3c3,0x301d333b,0xb15fb26d,
  0xb01db3fe,0x33fe301d,0xb0c42ed7,0xad64b3ea,0x326d33fe,0xaed72bc6,0xb3c3b33b,0x2248b0c4,0xb3c3b3fe,0xb15fb2dd,0xa8b2aed7,0x2ed728b2,
  0x30c4b15f,0x2ed7b01d,0x2bc6ad64,0x2248a8b2,0x2bc6b15f,0xb15f2bc6,0xb3ea3388,0xaed7326d,0xa8b2b15f,0xb38832dd,0x301d2d64,0x31edb3ea,
  0xb01db15f,0xa24833c3,0x30c4b388,0xb38830c4,0xb26db15f,0x333b301d,0xb3c3ad64,0x33fe28b2,0xb3c3b15f,0x31edabc6,0x28b23388,0xb33bb26d,
  0xb3eab15f,0xad64b2dd,0x32dd2d64,0x315f33ea,0xb2ddb15f,0xb3feb3c3,0xb26db388,0xad64b0c4,0xa8b22248,0xad642bc6,0xb01d2ed7,0xb15f30c4,
  0x301da248,0x33feb2dd,0x30c4b33b,0xad64a8b2,0xb26d2248,0xaed733c3,0x33c3aed7,0x2248b26d,0x33c3a248,0xb15fb01d,0x28b2333b,0x2ed7b3ea,
  0xb3ea2248,0x3388abc6,0xb2dd2ed7,0x31edb0c4,0x32dda248,0xa24832dd,0xb26db33b,0x338828b2,0xb0c42248,0xb33bb3c3,0x2bc6aed7,0x33fe326d,
  0x2bc6a248,0x31ed301d,0x33ea333b,0x333b33ea,0x30c4315f,0x2ed7301d,0x2bc62d64,0x224828b2,0x2bc6315f,0xb15fabc6,0xb3eab388,0xaed7b26d,
  0xa8b2315f,0xb388b2dd,0x301dad64,0x31ed33ea,0xb01d315f,0xa248b3c3,0x30c43388,0xb388b0c4,0xb26d315f,0x333bb01d,0xb3c32d64,0x33fea8b2,
  0xb3c3315f,0x31ed2bc6,0x28b2b388,0xb33b326d,0xb3ea315f,0xad6432dd,0x32ddad64,0x315fb3ea,0xb2dd315f,0xb3fe33c3,0xb26d3388,0xad6430c4,
  0xa8b2a248,0xad64abc6,0xb01daed7,0xb15fb0c4,0x301d2248,0x33fe32dd,0x30c4333b,0xad6428b2,0xb26da248,0xaed7b3c3,0x33c32ed7,0x2248326d,
  0x33c32248,0xb15f301d,0x28b2b33b,0x2ed733ea,0xb3eaa248,0x33882bc6,0xb2ddaed7,0x31ed30c4,0x32dd2248,0xa248b2dd,0xb26d333b,0x3388a8b2,
  0xb0c4a248,0xb33b33c3,0x2bc62ed7,0x33feb26d,0x2bc62248,0x31edb01d,0x33eab33b,0x333bb3ea,0x326d31ed,0x333b32dd,0x33c33388,0x33fe33ea,
  0x33c331ed,0x31ed33c3,0xa8b22d64,0xb33bb0c4,0x33ea31ed,0xad64301d,0xb2ddb388,0x315fa8b2,0x32dd31ed,0xb3feabc6,0x326dad64,0xad64326d,
  0x30c431ed,0xaed7b2dd,0x2bc63388,0xa248b3ea,0x2bc631ed,0x315fb3c3,0xb3ea2d64,0x2ed730c4,0xa8b231ed,0x3388b01d,0x301db388,0xb1ed28b2,
  0xb01d31ed,0x22482bc6,0x30c4ad64,0x3388b26d,0x33ea33fe,0x338833c3,0x32dd333b,0x31ed326d,0xb2ddb3fe,0xa248b01d,0x326d2ed7,0x338833ea,
  0x30c433fe,0xb33babc6,0xabc6b33b,0x33fe30c4,0xabc6b3fe,0x31ed32dd,0xb3eaaed7,0x333ba8b2,0xa8b233fe,0x2d64b3c3,0xb01d333b,0x315fb26d,
  0x301db3fe,0xb3fe301d,0x30c42ed7,0x2d64b3ea,0xb26d33fe,0x2ed72bc6,0x33c3b33b,0xa248b0c4,0x33c3b3fe,0x315fb2dd,0x28b2aed7,0xaed728b2,
  0xb0c4315f,0xaed7301d,0xabc62d64,0xa24828b2,0xabc6315f,0x315fabc6,0x33eab388,0x2ed7b26d,0x28b2315f,0x3388b2dd,0xb01dad64,0xb1ed33ea,
  0x301d315f,0x2248b3c3,0xb0c43388,0x3388b0c4,0x326d315f,0xb33bb01d,0x33c32d64,0xb3fea8b2,0x33c3315f,0xb1ed2bc6,0xa8b2b388,0x333b326d,
  0x33ea315f,0x2d6432dd,0xb2ddad64,0xb15fb3ea,0x32dd315f,0x33fe33c3,0x326d3388,0x2d6430c4,0x28b2a248,0x2d64abc6,0x301daed7,0x315fb0c4,
  0xb01d2248,0xb3fe32dd,0xb0c4333b,0x2d6428b2,0x326da248,0x2ed7b3c3,0xb3c32ed7,0xa248326d,0xb3c32248,0x315f301d,0xa8b2b33b,0xaed733ea,
  0x33eaa248,0xb3882bc6,0x32ddaed7,0xb1ed30c4,0xb2dd2248,0x2248b2dd,0x326d333b,0xb388a8b2,0x30c4a248,0x333b33c3,0xabc62ed7,0xb3feb26d,
  0xabc62248,0xb1edb01d,0xb3eab33b,0xb33bb3ea,0xb26d31ed,0xb33b32dd,0xb3c33388,0xb3fe33ea,0xb3c331ed,0xb1ed33c3,0x28b22d64,0x333bb0c4,
  0xb3ea31ed,0x2d64301d,0x32ddb388,0xb15fa8b2,0xb2dd31ed,0x33feabc6,0xb26dad64,0x2d64326d,0xb0c431ed,0x2ed7b2dd,0xabc63388,0x2248b3ea,
  0xabc631ed,0xb15fb3c3,0x33ea2d64,0xaed730c4,0x28b231ed,0xb388b01d,0xb01db388,0x31ed28b2,0x301d31ed,0xa2482bc6,0xb0c4ad64,0xb388b26d,
  0xb3ea33fe,0xb38833c3,0xb2dd333b,0xb1ed326d,0x32ddb3fe,0x2248b01d,0xb26d2ed7,0xb38833ea,0xb0c433fe,0x333babc6,0x2bc6b33b,0xb3fe30c4,
  0x2bc6b3fe,0xb1ed32dd,0x33eaaed7,0xb33ba8b2,0x28b233fe,0xad64b3c3,0x301d333b,0xb15fb26d,0xb01db3fe,0x33fe301d,0xb0c42ed7,0xad64b3ea,
  0x326d33fe,0xaed72bc6,0xb3c3b33b,0x2248b0c4,0xb3c3b3fe,0xb15fb2dd,0xa8b2aed7,0x2ed728b2,0x29ed29ed,0x29ed29ed,0x29ed29ed,0x29ed29ed,
  0x2bc32a6d,0x2add2bea,0x23c628c4,0xa81da0b2,0x2bc32add,0xa3c6281d,0xabc3aadd,0x23c6a81d,0x29ed2b3b,0xabfea564,0x295fa6d7,0x1a482b88,
  0x25642b88,0xa564ab88,0x25642b88,0xa564ab88,0xa0b22bc3,0x2a6daadd,0xabea23c6,0x28c4281d,0xa8c42bea,0x2a6da0b2,0x28c4abea,0xaa6d20b2,
  0xab3b2bfe,0xa564295f,0x26d79a48,0x2b88a9ed,0x29ed29ed,0x29ed29ed,0x29ed29ed,0x29ed29ed,0xabc3aa6d,0xaaddabea,0xa3c6a8c4,0x281d20b2,
  0x2bc32add,0xa3c6281d,0xabc3aadd,0x23c6a81d,0xa9edab3b,0x2bfe2564,0xa95f26d7,0x9a48ab88,0x25642b88,0xa564ab88,0x25642b88,0xa564ab88,
  0x20b2abc3,0xaa6d2add,0x2beaa3c6,0xa8c4a81d,0xa8c42bea,0x2a6da0b2,0x28c4abea,0xaa6d20b2,0x2b3babfe,0x2564a95f,0xa6d71a48,0xab8829ed,
  0x295f295f,0x295f295f,0x295f295f,0x295f295f,0x23c628c4,0xa81da0b2,0xabc3aa6d,0xaaddabea,0xa3c6281d,0xabc3aadd,0x23c6a81d,0x2bc32add,
  0xa95f26d7,0x9a48ab88,0x29ed2b3b,0xabfea564,0xab882564,0x2b88a564,0xab882564,0x2b88a564,0xabea23c6,0x28c4281d,0x20b2abc3,0xaa6d2add,
  0xaa6d20b2,0xa8c42bea,0x2a6da0b2,0x28c4abea,0xa6d71a48,0xab8829ed,0xab3b2bfe,0xa564295f,0x295f295f,0x295f295f,0x295f295f,0x295f295f,
  0xa3c6a8c4,0x281d20b2,0x2bc32a6d,0x2add2bea,0xa3c6281d,0xabc3aadd,0x23c6a81d,0x2bc32add,0x295fa6d7,0x1a482b88,0xa9edab3b,0x2bfe2564,
  0xab882564,0x2b88a564,0xab882564,0x2b88a564,0x2beaa3c6,0xa8c4a81d,0xa0b22bc3,0x2a6daadd,0xaa6d20b2,0xa8c42bea,0x2a6da0b2,0x28c4abea,
  0x26d79a48,0x2b88a9ed,0x2b3babfe,0x2564a95f,0xabfe2bfe,0xabfe2bfe,0xabfe2bfe,0xabfe2bfe,0xaadd2bea,0xa3c628c4,0x281da0b2,0x2bc3aa6d,
  0xa81d2bc3,0x2adda3c6,0x281dabc3,0xaadd23c6,0x9a482b88,0x29edab3b,0xabfe2564,0x295f26d7,0x26d72b3b,0xa6d7ab3b,0x26d72b3b,0xa6d7ab3b,
  0x2a6d2add,0xabeaa3c6,0x28c4a81d,0x20b22bc3,0x2bea2a6d,0xa0b228c4,0xabeaaa6d,0x20b2a8c4,0x2b8829ed,0x2b3b2bfe,0x2564295f,0xa6d79a48,
  0xabfe2bfe,0xabfe2bfe,0xabfe2bfe,0xabfe2bfe,0x2addabea,0x23c6a8c4,0xa81d20b2,0xabc32a6d,0xa81d2bc3,0x2adda3c6,0x281dabc3,0xaadd23c6,
  0x1a48ab88,0xa9ed2b3b,0x2bfea564,0xa95fa6d7,0x26d72b3b,0xa6d7ab3b,0x26d72b3b,0xa6d7ab3b,0xaa6daadd,0x2bea23c6,0xa8c4281d,0xa0b2abc3,
  0x2bea2a6d,0xa0b228c4,0xabeaaa6d,0x20b2a8c4,0xab88a9ed,0xab3babfe,0xa564a95f,0x26d71a48,0x1a489a48,0x1a489a48,0x1a489a48,0x1a489a48,
  0x281da0b2,0x2bc3aa6d,0x2addabea,0x23c6a8c4,0x2adda3c6,0x281dabc3,0xaadd23c6,0xa81d2bc3,0x2bfea564,0xa95fa6d7,0x9a482b88,0x29edab3b,
  0x2b3ba6d7,0xab3b26d7,0x2b3ba6d7,0xab3b26d7,0x28c4a81d,0x20b22bc3,0xaa6daadd,0x2bea23c6,0x20b2a8c4,0x2bea2a6d,0xa0b228c4,0xabeaaa6d,
  0xa564a95f,0x26d71a48,0x2b8829ed,0x2b3b2bfe,0x1a489a48,0x1a489a48,0x1a489a48,0x1a489a48,0xa81d20b2,0xabc32a6d,0xaadd2bea,0xa3c628c4,
  0x2adda3c6,0x281dabc3,0xaadd23c6,0xa81d2bc3,0xabfe2564,0x295f26d7,0x1a48ab88,0xa9ed2b3b,0x2b3ba6d7,0xab3b26d7,0x2b3ba6d7,0xab3b26d7,
  0xa8c4281d,0xa0b2abc3,0x2a6d2add,0xabeaa3c6,0x20b2a8c4,0x2bea2a6d,0xa0b228c4,0xabeaaa6d,0x2564295f,0xa6d79a48,0xab88a9ed,0xab3babfe,
  0xa95fa95f,0xa95fa95f,0xa95fa95f,0xa95fa95f,0xa3c6a8c4,0x281d20b2,0x2bc32a6d,0x2add2bea,0x23c6a81d,0x2bc32add,0xa3c6281d,0xabc3aadd,
  0x295fa6d7,0x1a482b88,0xa9edab3b,0x2bfe2564,0x2b88a564,0xab882564,0x2b88a564,0xab882564,0x2beaa3c6,0xa8c4a81d,0xa0b22bc3,0x2a6daadd,
  0x2a6da0b2,0x28c4abea,0xaa6d20b2,0xa8c42bea,0x26d79a48,0x2b88a9ed,0x2b3babfe,0x2564a95f,0xa95fa95f,0xa95fa95f,0xa95fa95f,0xa95fa95f,
  0x23c628c4,0xa81da0b2,0xabc3aa6d,0xaaddabea,0x23c6a81d,0x2bc32add,0xa3c6281d,0xabc3aadd,0xa95f26d7,0x9a48ab88,0x29ed2b3b,0xabfea564,
  0x2b88a564,0xab882564,0x2b88a564,0xab882564,0xabea23c6,0x28c4281d,0x20b2abc3,0xaa6d2add,0x2a6da0b2,0x28c4abea,0xaa6d20b2,0xa8c42bea,
  0xa6d71a48,0xab8829ed,0xab3b2bfe,0xa564295f,0x29ed29ed,0x29ed29ed,0x29ed29ed,0x29ed29ed,0x2bc32a6d,0x2add2bea,0x23c628c4,0xa81da0b2,
  0x2bc32add,0xa3c6281d,0xabc3aadd,0x23c6a81d,0x29ed2b3b,0xabfea564,0x295fa6d7,0x1a482b88,0x25642b88,0xa564ab88,0x25642b88,0xa564ab88,
  0xa0b22bc3,0x2a6daadd,0xabea23c6,0x28c4281d,0xa8c42bea,0x2a6da0b2,0x28c4abea,0xaa6d20b2,0xab3b2bfe,0xa564295f,0x26d79a48,0x2b88a9ed,
  0x29ed29ed,0x29ed29ed,0x29ed29ed,0x29ed29ed,0xabc3aa6d,0xaaddabea,0xa3c6a8c4,0x281d20b2,0x2bc32add,0xa3c6281d,0xabc3aadd,0x23c6a81d,
  0xa9edab3b,0x2bfe2564,0xa95f26d7,0x9a48ab88,0x25642b88,0xa564ab88,0x25642b88,0xa564ab88,0x20b2abc3,0xaa6d2add,0x2beaa3c6,0xa8c4a81d,
  0xa8c42bea,0x2a6da0b2,0x28c4abea,0xaa6d20b2,0x2b3babfe,0x2564a95f,0xa6d71a48,0xab8829ed,0x9a481a48,0x9a481a48,0x9a481a48,0x9a481a48,
  0xa81d20b2,0xabc32a6d,0xaadd2bea,0xa3c628c4,0xaadd23c6,0xa81d2bc3,0x2adda3c6,0x281dabc3,0xabfe2564,0x295f26d7,0x1a48ab88,0xa9ed2b3b,
  0xab3b26d7,0x2b3ba6d7,0xab3b26d7,0x2b3ba6d7,0xa8c4281d,0xa0b2abc3,0x2a6d2add,0xabeaa3c6,0xa0b228c4,0xabeaaa6d,0x20b2a8c4,0x2bea2a6d,
  0x2564295f,0xa6d79a48,0xab88a9ed,0xab3babfe,0x9a481a48,0x9a481a48,0x9a481a48,0x9a481a48,0x281da0b2,0x2bc3aa6d,0x2addabea,0x23c6a8c4,
  0xaadd23c6,0xa81d2bc3,0x2adda3c6,0x281dabc3,0x2bfea564,0xa95fa6d7,0x9a482b88,0x29edab3b,0xab3b26d7,0x2b3ba6d7,0xab3b26d7,0x2b3ba6d7,
  0x28c4a81d,0x20b22bc3,0xaa6daadd,0x2bea23c6,0xa0b228c4,0xabeaaa6d,0x20b2a8c4,0x2bea2a6d,0xa564a95f,0x26d71a48,0x2b8829ed,0x2b3b2bfe,
  0xabfe2bfe,0xabfe2bfe,0xabfe2bfe,0xabfe2bfe,0xaadd2bea,0xa3c628c4,0x281da0b2,0x2bc3aa6d,0xa81d2bc3,0x2adda3c6,0x281dabc3,0xaadd23c6,
  0x9a482b88,0x29edab3b,0xabfe2564,0x295f26d7,0x26d72b3b,0xa6d7ab3b,0x26d72b3b,0xa6d7ab3b,0x2a6d2add,0xabeaa3c6,0x28c4a81d,0x20b22bc3,
  0x2bea2a6d,0xa0b228c4,0xabeaaa6d,0x20b2a8c4,0x2b8829ed,0x2b3b2bfe,0x2564295f,0xa6d79a48,0xabfe2bfe,0xabfe2bfe,0xabfe2bfe,0xabfe2bfe,
  0x2addabea,0x23c6a8c4,0xa81d20b2,0xabc32a6d,0xa81d2bc3,0x2adda3c6,0x281dabc3,0xaadd23c6,0x1a48ab88,0xa9ed2b3b,0x2bfea564,0xa95fa6d7,
  0x26d72b3b,0xa6d7ab3b,0x26d72b3b,0xa6d7ab3b,0xaa6daadd,0x2bea23c6,0xa8c4281d,0xa0b2abc3,0x2bea2a6d,0xa0b228c4,0xabeaaa6d,0x20b2a8c4,
  0xab88a9ed,0xab3babfe,0xa564a95f,0x26d71a48,0x3bfb3bff,0x3be53bf2,0x3bbf3bd4,0x3b873ba5,0x3bd03bfb,0x3b013b7c,0x399d3a60,0x378538bc,
  0x35173b52,0xbbc9b7c8,0xb074ba9b,0x3bfe391b,0x319e3b27,0xbbf3b979,0x363cb80a,0x3a2d3bc5,0xba093986,0x3a7eb8f8,0xbae5385f,0x3b3db77a,
  0xbabd393c,0x3bb0b699,0xbc00305b,0x3ba730d7,0xbb2a35c8,0xb8353bb2,0x3a64b1e8,0x3962bbf7,0xba90350b,0xba413bff,0x3602340e,0x3bf6bad8,
  0xac6aa5e4,0xb122af59,0xb402b294,0xb56ab4b7,0xb2deac9c,0xb7bdb5a5,0xb9b3b8d6,0xbb10ba73,0xbb96b676,0xb359bafe,0x3bec3884,0x2a163a29,
  0xbbe0b72c,0x2f27b9d6,0x3b5e3ae8,0xb91633a2,0xb941b9c9,0x38ad3a45,0xb80fbab3,0x36d23b13,0xb850ba0d,0x346f3b4a,0x1fdbbbed,0xb4ab3be8,
  0x3721bb76,0xbace3463,0xb8d13bdd,0x39ebadfb,0x3894bb98,0xb8fd281f,0xbb6a3bbd,0x2e2d3825,0x3b3f3b65,0x3ae83b16,0x3a813ab6,0x3a0d3a49,
  0x3263356a,0xad972b43,0xb5dfb359,0xb8eeb7f3,0xa9b139aa,0xbbedba25,0x3340b889,0x3b983afb,0xbaa2aa16,0xb4cfbb8e,0x3c0038ad,0xb44b38e5,
  0xbb853625,0x3bbdb4c3,0xbbe432ad,0x3bfbaf8b,0xbaacb6d2,0x39243954,0xb65fbace,0x2fbd3bb8,0xb9661648,0xba603bf8,0x383a31cf,0x3b27bbb3,
  0x3219b9eb,0xbb1836f4,0xb9903be5,0x37dd3010,0xb6c6b61a,0xb80ab76f,0xb8a8b85a,0xb93cb8f3,0xbbd7bb87,0xbbf8bbfd,0xbb71bbc9,0xba4dbaf1,
  0xbbfeb9a6,0x305bb91f,0x3bcb3a97,0xb50b37d2,0xb87abbfe,0x3ba13546,0x24523a7e,0xbbb5ba54,0xb576bb63,0x340e3ba3,0xb13bbbd3,0x2c9c3bf2,
  0x386abb3d,0xba2139f8,0x3b57b835,0xbbf13432,0x39e7bc00,0xb8d6adc9,0xbacb3bde,0x372c3457,0x3bdab962,0x3764bb35,0xb9c03122,0xbaf73bef,
  0x398b39cd,0x38fd3946,0x386538b2,0x37853815,0xba85b9c9,0xbb92bb1e,0xbbfebbdd,0xbbc2bbf5,0xb66b3682,0xbb01bb94,0x387fb371,0x3a2d3beb,
  0xbac7bb76,0x3a00ad33,0x36bb3bd4,0xbbeab79b,0xbc0026ad,0x3bf32c38,0xbbd6b109,0x3ba733eb,0x3153bbff,0xb70a3b9e,0x396bba9b,0xbade390c,
  0xb5d4b5bc,0xbbb03b2c,0x32013830,0x3bf6ba67,0x3bccbb52,0x2c06b92e,0xbb83385f,0xb8c73bab,0xb9c5b982,0xba41ba04,0xbab0ba7a,0xbb10bae1,
  0xb8a3b986,0xb52fb74e,0xa94db1e8,0x33d32e91,0xbb54bb4f,0x37bdb523,0x3a9e3bc8,0xb916308d,0x3840b5c8,0x394a3bf9,0xbb42b294,0xb0a6bb0a,
  0x251bbbff,0xaf273bfc,0x327cbbe6,0xb4ab3bc0,0x3be325e4,0xbb2fb4e7,0x39e33884,0xb81aba35,0x3b73bb78,0xb46fb715,0xbbdc3ad1,0x2e2d38cc,
  0x33283676,0x3bfcba19,0x3581bab3,0xba6b3493,0x363136dd,0x34cf3581,0x32c6341a,0x2fbd3153,0xbae1bb65,0xb970ba39,0xb715b889,0xb16cb4f3,
  0xb9a12a7a,0xb924bbfe,0x3a933042,0x37dd3bcc,0x308db9aa,0x3b453b07,0xb94632ad,0xb845bbfa,0xbb68b55e,0x3b1836bb,0xbabab805,0x3a4d38a3,
  0x3bc0b625,0xbbfe2ec3,0x3b9431cf,0xba89b742,0x9cb6b95d,0xbbf8396b,0xb1b63a5c,0x3bb5b840,0x38cc9648,0x3b81bbac,0xac38b85a,0xbbce3933,
  0xbb60bb3a,0xbba1bb83,0xbbd2bbbc,0xbbf1bbe3,0x3815361a,0x39df3907,0x3b2c3a97,0x3be23b9c,0xb9afbbfd,0x3a21294d,0x388e3bee,0xbaf7b328,
  0x3beb39a6,0xb6af37a6,0xba04bbd3,0x3ac42d00,0x360ebb89,0xb7643b42,0x3855baeb,0xb8ee3a85,0x33eb3b63,0x28e8bbf5,0xb5233bde,0x389ebb21,
  0x3c00b9f0,0x2d97b9e3,0xbbdf38db,0xb44b3ac7,0xba673c00,0x358d3487,0x3bfcbab6,0x330fba15,0x3b7a3bf1,0x394a3a93,0x33893764,0xb3d39cb6,
  0x3afb3be2,0x35eb3946,0xb4c328e8,0xbaa9b8cc,0x27763af7,0xbb2fbaba,0x3a76ad97,0x30a63b60,0xaf8b3ac4,0xb994bb94,0x3bf8358d,0xb8743815,
  0xbb4c38ee,0x3bfcb1b6,0xbad5b4cf,0x381a39af,0xbbb3389e,0x3b592c38,0xb76fb970,0xb24b3beb,0xb9d2344b,0xbb923bd2,0xb0f03924,0x3a6bb60e,
  0xb8f3330f,0xbc003b2c,0xb91f3b45,0x323233eb,0xb5b1afbd,0xba00b88e,0xbbc6bb18,0xbbc2bc00,0xb7d2b16c,0xbb6fba04,0xbba3bbfe,0xb86fba67,
  0xbbffb7dd,0x370ab855,0x38b73bf8,0xbbeab631,0xbbf2b845,0x39bcb523,0x2dc93b81,0xbaa5bae1,0xb68dba4d,0xac063bdf,0x382abba1,0xbade39a1,
  0xb457ba89,0xb6543bfc,0x3b16b9df,0xbbd8308d,0x397dbbb5,0xb52fb2c6,0xbbe73a21,0xb8c73b68,0x3a49bbce,0x2311b715,0xba2536af,0xbbd93bc0,
  0xb958b785,0xbb81ba9e,0xbbefbbf3,0xba89bb73,0xbbf7bbc2,0xb9b8bb42,0xaf59b70a,0x384a3328,0xbb8bba2d,0x39dfb27c,0x34263bb0,0xbbceb98b,
  0xb4b7bbea,0x3b6c39e3,0xbafe2c06,0x3185ba85,0xaadebba7,0xb6af3bdc,0x3a58ba41,0xbbe2366b,0x3a29bade,0xbc003581,0x3a45352f,0xb2f7bac7,
  0x3b37bbf6,0x28e8b865,0xbaee37bd,0xbac43c00,0x3b13b8c7,0x3b5cbbfe,0x3463b94a,0xb8993153,0xb9f4bb10,0xb58db87f,0x3029af27,0x389e35d4,
  0x2dfbb3d3,0x399936bb,0x3bf23b2f,0x3ac13bcc,0x3552b916,0x39703bd6,0xbbbab46f,0x330fb9c5,0x3ba530a6,0xb5f7396b,0xb7c8bbfc,0x3be138a3,
  0x3bfdb4ab,0xbb45b201,0x38e038fd,0xb16cbb54,0x391b381a,0xa17fbb83,0xb8f83b92,0x3bcfb840,0x36e82e2d,0x3bfebab0,0x37febb01,0xb845251b,
  0xb77a3a6b,0x3648294d,0x3bb2ba00,0x3a8cbbe3,0xb742b93c,0x2311b340,0x37a6340e,0x3aa93966,0x3b963a4d,0x3b7f3c00,0x380f3a21,0xb0be3219,
  0x3933b50b,0x35eb3be4,0xbbf5b8d6,0x3874b6c6,0x39413bb5,0xbbffb65f,0x38d1b764,0x33ba3bd7,0x3b9c2c9c,0xb994b83a,0x34873ae8,0x324bbbfe,
  0xb7213bf1,0x3b47b990,0xbbbf2d97,0x38c1387a,0x2d00372c,0x3b59b8a8,0x3a39bbed,0xb232b576,0xbbfb3af7,0xb9743b71,0x307434cf,0x3adbb86a,
  0x3b213a0d,0x3c003bcb,0x3b073bbd,0x386f39e7,0x351738ee,0xb599a452,0xbae5b924,0xbbe9bbda,0x3a153b98,0xbb6fb13b,0x2ec3ba60,0x3aa53b3f,
  0xba09344b,0xa884bb57,0x3a643b18,0xbbc3b263,0xb4f33bfb,0x39bcbacb,0xbbac380a,0x3bd8a9b1,0xbb2aafbd,0x36a439c0,0x3402bbf8,0xba6f3aa2,
  0xbbfa3b27,0xb6543a81,0x3907b05b,0x3bd9bb85,0x2c6ab7dd,0xb9da35df,0xbbec3ba1,0xb8203aac,0x3bf53b87,0x3b6c3bec,0x392e3a7e,0x32f73721,
  0xb9e7b785,0xbbfcbb5e,0xba81bbb0,0xb43eb894,0x379b3bfe,0xbc00b80f,0x374eb835,0x38993bfb,0xbb3fba2d,0x3b329fdb,0xb3403a41,0xb8eabbd0,
  0xb90c3b3d,0x3b5cb8d1,0xbbf93122,0x3ac13517,0x29b1bba7,0xb94f3b6a,0x3be4b7bd,0xbaf4b19e,0xbbab3962,0xb9993bbf,0x34e73359,0x3be1ba09,
  0x3b85bbf6,0x353ab99d,0xb83a2f27,0xbbf03abd,0x2e91356a,0xb5f7b074,0xba19b8ad,0xbbcfbb2a,0xb966bb10,0xaba7b63c,0x38a8346f,0x3bb73a90,
  0xbb0aaa16,0xa17fbae5,0x3b1e3ace,0xba8c2c6a,0x36c6b916,0x36ff3c00,0xbbcbb8fd,0x3a50b2de,0xba35b6d2,0x36483a64,0x2d33bbe5,0xb84a3b96,
  0x3bfeb4ab,0xb9fcb602,0x313b3b01,0x37e8bbe0,0x3493b9eb,0xb9b83402,0xbb9e3bc9,0xb1853941,0x35762e2d,0x3b90b9b3,0x3acbbbf3,0x2fefb850,
  0x3a543bcf,0x2884374e,0xb9f8b648,0xbbe9bbab,0x398b3bb7,0xb4db3340,0xbbdcb9fc,0xb911bb85,0xb4323a8c,0xb6a4bbf9,0x3b3539b8,0xbbc3ae91,
  0xb66b3a50,0xad65bbe4,0x38653b90,0xbb0db966,0xbbef384a,0x39da34e7,0x2b43bb6c,0xba6f3b0a,0xbc0037e8,0x3759383a,0x387fbbfc,0xbbf636c6,
  0xb7f33185,0xbb7f3a19,0xbb8e3c00,0xb8203a35,0xb5d42fef,0xba1d38a8,0xbbd63b32,0xbba93bfe,0xb8e5b2f7,0xbbffbb1e,0xb954bb5c,0x30beb493,
  0xb9c5b43e,0xbb9fbbcb,0xb201b94f,0x3a313576,0xbbb8b899,0x3b47ad33,0xb6f43999,0xb3babbf5,0xbb54b8ea,0x3bf9313b,0xbab0353a,0x3790b9e7,
  0xb010bac1,0xb9743b9e,0x3bfdb5f7,0xb8c1b79b,0x251bbaf4,0xbb1b3acb,0x3a9e2ba7,0x2e5fbb3f,0x3af1bbe1,0x3599b92e,0xb546a17f,0xbadb390c,
  0x3b73bbf0,0x3929ba81,0x327cb6ff,0xb49f29b1,0xb825baa9,0x353aaec3,0x3b7c3994,0x3af43bfa,0x360eb0be,0x3bf43a64,0x388e3b47,0xb7372c6a,
  0x38bcb874,0x2ba73bac,0xb979bb59,0x3bf03742,0x3c0033ba,0xbb043402,0x3855b974,0xacce3b96,0x3bc5b24b,0xb6ffb907,0xb6993c00,0x3bb7b933,
  0x363138c1,0x3902bbec,0xbbdf3599,0x34ff3941,0x30d73232,0x39fcb7a6,0x3bffbb6f,0x3a50bb9c,0xb9a13adb,0xb47b380f,0x32c62884,0x3937b721,
  0x3ad8386f,0x3b903bf5,0x35a539bc,0xb7e8ad00,0x3b683be9,0x2ef538d1,0xba93b6a4,0xbb24bbfb,0x3a733aa5,0xbbfcb487,0x39d6b654,0xafef3b21,
  0x1cb63bc3,0xb7b2bbbf,0x3aba39da,0xbbfab517,0xb3a23bd8,0x3b32ba39,0xbb4a2311,0x343e3a15,0xbb603a6f,0x3a3d3074,0x31b6bb7f,0xbb9a3a09,
  0xbbe83bd9,0xb94f3b07,0xa81f35eb,0x38eab4f3,0xb9af3820,0xbbae3ae5,0xbbd23bff,0xba113b2a,0x319e389e,0xb929b426,0xbc00bb45,0xb911bb37,
  0xbbffbac1,0xb805bafe,0x382a217f,0x3bfd3b13,0xbabd330f,0x34dbba58,0x36023bfe,0xbb0db9f4,0xb68dbbe1,0x3a5c3a45,0xbbe7b648,0x3b89adfb,
  0xba90b16c,0x2d653aee,0x39b3bb81,0xbbf63552,0x397dbbcf,0xbbbc3463,0x338939b8,0x39f0bba5,0x32deb845,0xb7593029,0xbb5e39df,0xbba93bfd,
  0x3b7aba8c,0x3beebbf2,0x3a76bb6c,0x36ddb91b,0xbbe0ba89,0xba1dbbba,0x1fdbb6af,0x3a3136e8,0xa776b84a,0x3aeb37c8,0x3ad53c00,0xaa7a377a,
  0xb850bbce,0x3b9f38e0,0xbb6a28e8,0x3790b958,0x3b4cb185,0xb8db38f8,0x30f0bb5c,0x355e3bf7,0x3894bbe2,0xbbf937fe,0x399d358d,0x2e5fbb8b,
  0x39d232f7,0x341abbb2,0xbbc63999,0x395d34b7,0x3bd0bac4,0x3b1bbbef,0x363cb970,0xb49faade,0xb5b13899,0x30422f59,0x38b7b5f7,0x3b3aba29,
  0x3219b3d3,0x3b0438b7,0x3b713bfc,0x34ff397d,0x36e83aa9,0xb8b2adc9,0xbbefbb59,0xb5bcba49,0x3bd730a6,0xb902382a,0xa452bb92,0x39373b7a,
  0xb9583874,0x3371bb16,0x34263c00,0xb982bafb,0x387a381a,0x347bbbe7,0xbb573a00,0x3b242776,0xbb8b324b,0x31093a25,0x3a58bb6f,0xbb4f2f8b,
  0xb86a3a6b,0x2ef53389,0x39c0b70a,0x3bfabb4c,0xaadeb232,0xb83034c3,0xbaee39bc,0xbbff3bb3,0x3bda3bc2,0x37b23a76,0xb5df2c06,0xbb9ab9d2,
  0xbb37b86f,0xba7abbf8,0x3029b654,0x3b7838f3,0x32633bea,0xba3dbad5,0x3c00352f,0xba1135b1,0xb9f4baa5,0x3bc8376f,0xbbba2311,0x39cdb7d2,
  0xbaa23ade,0x3baeb0f0,0xb65fb94a,0xb7373bff,0x3552bbd8,0xbbe6391f,0x38e035eb,0x3682bbf2,0xbaac38c7,0xbbf43bc6,0xb9903b2f,0xacce368d,
  0x3bfdbbd9,0x3ad1bba3,0x37feb994,0x26adb457,0x38a33b9a,0xb8dba452,0xbb83bbae,0x2a7ab86a,0x37423b78,0xbab6b426,0xb907bbe6,0x39aa2ade,
  0xb8403a11,0x341abb57,0x294d3bf4,0xb55ebbda,0xb93339cd,0x3889ba58,0xb7a63ad1,0x3625bb37,0xbbe33737,0x304239c0,0x3b42bb04,0xb95db263,
  0xbb9c3682,0xb2ad3aee,0x3bf5b8b2,0x1648b9f4,0xb3282cce,0xb80535df,0xb9e33902,0xbb3a3aa2,0xad0026ad,0xb1cf3029,0xb4873371,0xb61a3552,
  0xba85b4ff,0xba5cbc00,0x3581b47b,0x3bfd3aac,0xbb21b5bc,0xb85abbba,0x3a393109,0x39a63bfd,0xbac7b937,0x3bbc365f,0xbbfeaef5,0x3b89b219,
  0xba15b982,0x3a9738e0,0xbb07b830,0x3b6336e8,0x3153bb24,0xbbee3990,0x36bb37b2,0x39f0bbd7,0x34f3bb4f,0xbbd337fe,0xaec33a7a,0x3c00b958,
  0x3bccbbfa,0x3aebbb71,0x396bba3d,0x36ddb87a,0x3bfabbff,0x3bdebbef,0x3bacbbc8,0x3b65bb8b,0x3bc03911,0x38303b6a,0xb946ad65,0xbb4fbbd0,
  0x3a353bfd,0xb85f30f0,0xbb1ebbbc,0x35c8b5b1,0x38cc3b0d,0xba7ab99d,0x3b943759,0xbbffb19e,0xb4933b89,0x31e8bbc6,0xad333bee,0xa5e4bbff,
  0xb8153bf6,0x3bc8b63c,0xac38ba1d,0xbb783abd,0xbbf539f0,0x329438b7,0x3b9ebaeb,0xb676b68d,0xbbeb3ba9,0xbbe63c00,0xbb2c3b9f,0xb9cd3a90,
  0xb79b36dd,0xb884382a,0xb92e38db,0xb9c9397d,0x33eb3a31,0xbad1b602,0xba04bbf9,0x3682b2de,0xb90c2a7a,0xbab3bbe7,0x374eb41a,0x3b763b7a,
  0xba673790,0x38b2b9b3,0xb5233b1b,0x26adbbe0,0xbbabb55e,0x3bdd3389,0xbbf9b042,0x3bff2776,0xbae12e5f,0xb3713b5e,0x3bfcb929,0xb5bcb850,
  0xae91b95d,0xbbd43a76,0x34e73805,0x3b52bb4c,0x308db49f,0xb1091fdb,0xb71534db,0xb9823894,0x3b0abb3a,0x3a9bbad5,0x3a19ba5c,0x3986b9d2,
  0x2f8bb7e8,0x3bde3979,0x376f3b32,0xb9aab0d7,0x3bb83b24,0xb1223855,0xbbfdba3d,0xaa16b9a1,0x3bb3afef,0xbab63699,0x391fb94f,0xb6253ad8,
  0x30103bfa,0xb359bbdf,0x35463bae,0xb6d2bb68,0x38f3343e,0x3889bbff,0xbba3353a,0x96483a73,0xbaf13b9a,0x38ad32c6,0x39f8bbf4,0xb9eb9cb6,
  0xb7d238ea,0xb2ad35a5,0x2dc92ba7,0x361ab3a2,0xba543a11,0xbace3a93,0xbb353b04,0xbb873b60,0x3bf23af4,0x31cf39d6,0xbb16b6ff,0xb9a6bbe8,
  0xb4323737,0xbbe5baba,0x2b43b902,0x3bfe39af,0x34573bf0,0xb85abb4a,0x3a2539fc,0xbb63b825,0xbbef2cce,0x3bc9b1b6,0xbb8e347b,0x3b3db60e,
  0xba493bb7,0x3a97a81f,0x34c3bb90,0xbc0038bc,0xb7f3b4ff,0xba7e3bd2,0x39542ef5,0x3962bc00,0xbafb3a50,0xbbd33b7c,0xbbf83bfc,0xbb653bc5,
  0x38e5b937,0x3835b88e,0x36f4b7b2,0x356ab631,0xbb13bbe9,0x31e8b6f4,0x3bf239da,0x36763af1,0x3be83911,0x340e3ab0,0xbb7cb759,0xb72cbb73,
  0x2dfbbbc3,0x32943bfd,0xb7c8bb7f,0x39c93a54,0x38253b0d,0xb8d6ba9e,0x39793a1d,0xba0db98b,0x3ba5ba6f,0xb884b546,0xb8f83bff,0x3b76b432,
  0xb8bc3bf6,0x3ae8b27c,0x3699bb9f,0xbb98366b,0x391bb820,0x3ab3b9f8,0x3bb2bb47,0x3bffbbef,0xbbc53ba9,0xbbed3bdc,0xbbff3bf9,0xbbfb3c00,
  0x377ab0be,0x3bdd3b35,0x2f593974,0xbb52b7f3,0x30d73a31,0xbbbdb865,0xb5a5bb1b,0x3b2735d4,0x3bf733ba,0xbbd42b43,0x3afeb599,0xb98638e5,
  0xbad83790,0x3a60b87f,0xb9d63929,0x393cb9c5,0x34b738c1,0x3a9bbb8e,0xba45a884,0xb5c83bb8,0xba732e5f,0xb80a3bd6,0x3b4ab4db,0x350bbb54,
  0xba293adb,0xb85f3954,0xb46336a4,0x25e43010,0x33a2b49f,0x305bb201,0x281fad65,0xac9c251b,0x3f803f80,0x3f803f80,0x3f803f80,0x3f803f80,
  0x3f803f80,0x3f803f80,0x3f803f80,0x3f803f80,0x3f803f80,0x3f803f80,0x3f803f80,0x3f803f80,0x3f803f80,0x3f803f80,0x3f803f80,0x3f803f80,
  0x3f803f80,0x3f803f80,0x3f803f80,0x3f803f80,0x3f803f80,0x3f803f80,0x3f803f80,0x3f803f80,0x3f803f80,0x3f803f80,0x3f803f80,0x3f803f80,
  0x3f803f80,0x3f803f80,0x3f803f80,0x3f803f80,0x3f803f80,0x3f803f80,0x3f803f80,0x3f803f80,0x3f803f80,0x3f803f80,0x3f803f80,0x3f803f80,
  0x3f803f80,0x3f803f80,0x3f803f80,0x3f803f80,0x3f803f80,0x3f803f80,0x3f803f80,0x3f803f80,0x3f803f80,0x3f803f80,0x3f803f80,0x3f803f80,
  0x3f803f80,0x3f803f80,0x3f803f80,0x3f803f80,0x3f803f80,0x3f803f80,0x3f803f80,0x3f803f80,0x3f803f80,0x3f803f80,0x3f803f80,0x3f803f80,
  0x3f803f80,0x3f803f80,0x3f803f80,0x3f803f80,0x3f803f80,0x3f803f80,0x3f803f80,0x3f803f80,0x3f803f80,0x3f803f80,0x3f803f80,0x3f803f80,
  0x3f803f80,0x3f803f80,0x3f803f80,0x3f803f80,0x3f803f80,0x3f803f80,0x3f803f80,0x3f803f80,0x3f803f80,0x3f803f80,0x3f803f80,0x3f803f80,
  0x3f803f80,0x3f803f80,0x3f803f80,0x3f803f80,0x3f803f80,0x3f803f80,0x3f803f80,0x3f803f80,0x3f803f80,0x3f803f80,0x3f803f80,0x3f803f80,
  0x3f803f80,0x3f803f80,0x3f803f80,0x3f803f80,0x3f803f80,0x3f803f80,0x3f803f80,0x3f803f80,0x3f803f80,0x3f803f80,0x3f803f80,0x3f803f80,
  0x3f803f80,0x3f803f80,0x3f803f80,0x3f803f80,0x3f803f80,0x3f803f80,0x3f803f80,0x3f803f80,0x3f803f80,0x3f803f80,0x3f803f80,0x3f803f80,
  0x3f803f80,0x3f803f80,0x3f803f80,0x3f803f80,0x3f803f80,0x3f803f80,0x3f803f80,0x3f803f80,0x3f803f80,0x3f803f80,0x3f803f80,0x3f803f80,
  0x3f803f80,0x3f803f80,0x3f803f80,0x3f803f80,0x3f803f80,0x3f803f80,0x3f803f80,0x3f803f80,0x3f803f80,0x3f803f80,0x3f803f80,0x3f803f80,
  0x3f803f80,0x3f803f80,0x3f803f80,0x3f803f80,0x3f803f80,0x3f803f80,0x3f803f80,0x3f803f80,0x3f803f80,0x3f803f80,0x3f803f80,0x3f803f80,
  0x3f803f80,0x3f803f80,0x3f803f80,0x3f803f80,0x3f803f80,0x3f803f80,0x3f803f80,0x3f803f80,0x3f803f80,0x3f803f80,0x3f803f80,0x3f803f80,
  0x3f803f80,0x3f803f80,0x3f803f80,0x3f803f80,0x3f803f80,0x3f803f80,0x3f803f80,0x3f803f80,0x3f803f80,0x3f803f80,0x3f803f80,0x3f803f80,
  0x3f803f80,0x3f803f80,0x3f803f80,0x3f803f80,0x3f803f80,0x3f803f80,0x3f803f80,0x3f803f80,0x3f803f80,0x3f803f80,0x3f803f80,0x3f803f80,
  0x3f803f80,0x3f803f80,0x3f803f80,0x3f803f80,0x3f803f80,0x3f803f80,0x3f803f80,0x3f803f80,0x3f803f80,0x3f803f80,0x3f803f80,0x3f803f80,
  0x3f803f80,0x3f803f80,0x3f803f80,0x3f803f80,0x3f803f80,0x3f803f80,0x3f803f80,0x3f803f80,0x3f803f80,0x3f803f80,0x3f803f80,0x3f803f80,
  0x3f803f80,0x3f803f80,0x3f803f80,0x3f803f80,0x3f803f80,0x3f803f80,0x3f803f80,0x3f803f80,0x3f803f80,0x3f803f80,0x3f803f80,0x3f803f80,
  0x3f803f80,0x3f803f80,0x3f803f80,0x3f803f80,0x3f803f80,0x3f803f80,0x3f803f80,0x3f803f80,0x3f803f80,0x3f803f80,0x3f803f80,0x3f803f80,
  0x3f803f80,0x3f803f80,0x3f803f80,0x3f803f80,0x3f803f80,0x3f803f80,0x3f803f80,0x3f803f80,0x3f803f80,0x3f803f80,0x3f803f80,0x3f803f80,
  0x3f803f80,0x3f803f80,0x3f803f80,0x3f803f80,0x3f803f80,0x3f803f80,0x3f803f80,0x3f803f80,0x3f803f80,0x3f803f80,0x3f803f80,0x3f803f80,
  0x3f803f80,0x3f803f80,0x3f803f80,0x3f803f80,0x3f803f80,0x3f803f80,0x3f803f80,0x3f803f80,0x3f803f80,0x3f803f80,0x3f803f80,0x3f803f80,
  0x3f803f80,0x3f803f80,0x3f803f80,0x3f803f80,0x3f803f80,0x3f803f80,0x3f803f80,0x3f803f80,0x3f803f80,0x3f803f80,0x3f803f80,0x3f803f80,
  0x3f803f80,0x3f803f80,0x3f803f80,0x3f803f80,0x3f803f80,0x3f803f80,0x3f803f80,0x3f803f80,0x3f803f80,0x3f803f80,0x3f803f80,0x3f803f80,
  0x3f803f80,0x3f803f80,0x3f803f80,0x3f803f80,0x3f803f80,0x3f803f80,0x3f803f80,0x3f803f80,0x3f803f80,0x3f803f80,0x3f803f80,0x3f803f80,
  0x3f803f80,0x3f803f80,0x3f803f80,0x3f803f80,0x3f803f80,0x3f803f80,0x3f803f80,0x3f803f80,0x3f803f80,0x3f803f80,0x3f803f80,0x3f803f80,
  0x3f803f80,0x3f803f80,0x3f803f80,0x3f803f80,0x3f803f80,0x3f803f80,0x3f803f80,0x3f803f80,0x3f803f80,0x3f803f80,0x3f803f80,0x3f803f80,
  0x3f803f80,0x3f803f80,0x3f803f80,0x3f803f80,0x3f803f80,0x3f803f80,0x3f803f80,0x3f803f80,0x3f803f80,0x3f803f80,0x3f803f80,0x3f803f80,
  0x3f803f80,0x3f803f80,0x3f803f80,0x3f803f80,0x3f803f80,0x3f803f80,0x3f803f80,0x3f803f80,0x3f803f80,0x3f803f80,0x3f803f80,0x3f803f80,
  0x3f803f80,0x3f803f80,0x3f803f80,0x3f803f80,0x3f803f80,0x3f803f80,0x3f803f80,0x3f803f80,0x3f803f80,0x3f803f80,0x3f803f80,0x3f803f80,
  0x3f803f80,0x3f803f80,0x3f803f80,0x3f803f80,0x3f803f80,0x3f803f80,0x3f803f80,0x3f803f80,0x3f803f80,0x3f803f80,0x3f803f80,0x3f803f80,
  0x3f803f80,0x3f803f80,0x3f803f80,0x3f803f80,0x3f803f80,0x3f803f80,0x3f803f80,0x3f803f80,0x3f803f80,0x3f803f80,0x3f803f80,0x3f803f80,
  0x3f803f80,0x3f803f80,0x3f803f80,0x3f803f80,0x3f803f80,0x3f803f80,0x3f803f80,0x3f803f80,0x3f803f80,0x3f803f80,0x3f803f80,0x3f803f80,
  0x3f803f80,0x3f803f80,0x3f803f80,0x3f803f80,0x3f803f80,0x3f803f80,0x3f803f80,0x3f803f80,0x3f803f80,0x3f803f80,0x3f803f80,0x3f803f80,
  0x3f803f80,0x3f803f80,0x3f803f80,0x3f803f80,0x3f803f80,0x3f803f80,0x3f803f80,0x3f803f80,0x3f803f80,0x3f803f80,0x3f803f80,0x3f803f80,
  0x3f803f80,0x3f803f80,0x3f803f80,0x3f803f80,0x3f803f80,0x3f803f80,0x3f803f80,0x3f803f80,0x3f803f80,0x3f803f80,0x3f803f80,0x3f803f80,
  0x3f803f80,0x3f803f80,0x3f803f80,0x3f803f80,0x3f803f80,0x3f803f80,0x3f803f80,0x3f803f80,0x3f803f80,0x3f803f80,0x3f803f80,0x3f803f80,
  0x3f803f80,0x3f803f80,0x3f803f80,0x3f803f80,0x3f803f80,0x3f803f80,0x3f803f80,0x3f803f80,0x3f803f80,0x3f803f80,0x3f803f80,0x3f803f80,
  0x3f803f80,0x3f803f80,0x3f803f80,0x3f803f80,0x3f803f80,0x3f803f80,0x3f803f80,0x3f803f80,0x3f803f80,0x3f803f80,0x3f803f80,0x3f803f80,
  0x3f803f80,0x3f803f80,0x3f803f80,0x3f803f80,0x3f803f80,0x3f803f80,0x3f803f80,0x3f803f80,0x3f803f80,0x3f803f80,0x3f803f80,0x3f803f80,
  0x3f803f80,0x3f803f80,0x3f803f80,0x3f803f80,0x3f803f80,0x3f803f80,0x3f803f80,0x3f803f80,0x3f803f80,0x3f803f80,0x3f803f80,0x3f803f80,
  0x3f803f80,0x3f803f80,0x3f803f80,0x3f803f80,
};

__device__ __align__(128) float    g_part[16][8][2176];
__device__ __align__(128) float    g_kv[16][2176];
__device__ __align__(128) uint4    g_o[16 * 16 * 1024];
__device__ __align__(128) unsigned g_ocnt[2 * 16 * 32];
__device__ unsigned g_epoch[128];
#define GSTAMP(role, i) do {} while (0)
#define STAMP(role, i) do {} while (0)
#define PDUMP(role) do {} while (0)
#define PROF_SMEM 0

constexpr int STAGE_BYTES = 57344;
constexpr int OFF_H = 4 * 16384, OFF_VP = 9 * 16384, OFF_SPARE = 10 * 16384;
constexpr int OFF_XT = 172032, XT_STRIDE = 4112;
constexpr int OFF_BAR = 204928, OFF_EPOCH = OFF_BAR + 640, OFF_EX = OFF_BAR + 656, OFF_D = OFF_BAR + 672, OFF_SCALE = OFF_BAR + 704;
constexpr int OFF_F2F = 205824, OFF_F2I = 207872, OFF_F4 = 209920, OFF_ONES = 214016, OFF_KVB = 214016;
constexpr int OFF_STG = 219136, STG_STRIDE = 4352, SMEM_TOTAL = 232192 + PROF_SMEM;
enum { B_FULL1 = 0, B_EMPTY1 = 3, B_Q = 6, B_ODONE1 = 7, B_O1RDY = 8, B_H = 9, B_XRAW = 10, B_XT = 11, B_KV = 12, B_Y = 13,  B_AFREE = 15,
       B_STG = 18, B_ODONE = 24, B_XFREE = 25, B_FULL2 = 33, B_CONS2 = 49, B_SFREE = 14, B_PKRDY = 62, B_PKFREE = 64, B_H2 = 65, B_COUNT = 66 };
__host__ __device__ constexpr int bar_count(int i) {
  return i < B_EMPTY1 ? 1 : i < B_Q ? 4 : i == B_XT ? 4 : i == B_H ? 4 : i == B_SFREE ? 2 : i >= B_PKFREE ? 4 : i >= B_PKRDY ? 8 : i == B_KV ? 2 : i == B_Y ? 9
       : (i >= B_AFREE && i < B_STG) ? 16 : (i == B_ODONE || i == B_ODONE1) ? 8 : (i >= B_XFREE && i < B_FULL2) ? 4
       : i >= B_CONS2 ? 4 : (i >= B_FULL2 && i < B_FULL2 + 7) ? 2 : 1;
}
__host__ __device__ constexpr uint64_t bar_counts(int r) {
  uint64_t v = 0;
  for (int w = 0; w < 11; w++) v |= (uint64_t)(bar_count(1 + 11 * r + w) - 1) << (4 * w);
  return v;
}
constexpr uint64_t SLOT_A = 0x9645296452964594ull;
constexpr uint64_t SLOT_B = 0x7103871038710326ull;
constexpr uint32_t SW128 = 64 | (1u << 30);
constexpr int SPIN_LIMIT = 1 << 22;
#define PKV CU_TENSOR_MAP_L2_PROMOTION_L2_128B
#define BPRE B_KV
#define PFD 3
#define PD1 0
#define PD2 100
#define E1C 2
#define OSP 4
#define QPF 6
#define TSPLIT 1
#define OC0 2
#define OC1 2
#define BSPL 4
#define BPACE 250
#define NPOS 0
#define O1POS 1
#define HL1 4
#define OCH 3
#define O1D 3
#define QPOS 2
#define HOLD2 12
#define A0COL 0
#define KPOS 1
#define CWAIT 0
#define HSPL 12
#define BEARLY 3
#define BLATE B_KV
#define G2LA 0
#define G2W0 0
#define G2S 2
#define EPI2 1
#define HSTART 1500
#define PACE 800
#define OC 1

__device__ __forceinline__ uint32_t smem_u32(const void* p) { return (uint32_t)__cvta_generic_to_shared(p); }
__device__ __forceinline__ void wg_fence() { asm volatile("wgmma.fence.sync.aligned;" ::: "memory"); }
__device__ __forceinline__ void wg_commit() { asm volatile("wgmma.commit_group.sync.aligned;" ::: "memory"); }
template <int N> __device__ __forceinline__ void wg_wait() { asm volatile("wgmma.wait_group.sync.aligned %0;" ::"n"(N) : "memory"); }
template <int N> __device__ __forceinline__ void keep(float (&d)[N]) {
#pragma unroll
  for (int i = 0; i < N; i++) asm volatile("" : "+f"(d[i])::"memory");
}
__device__ __forceinline__ uint64_t mkdesc(uint32_t addr, uint32_t lbo, uint32_t sbo, uint32_t swz) {
  uint32_t lo = ((addr & 0x3FFFF) >> 4) | ((lbo >> 4) << 16), hi = (sbo >> 4) | (swz << 30);
  return ((uint64_t)hi << 32) | lo;
}
__device__ __forceinline__ void mbar_init(uint32_t bar, int cnt) { asm volatile("mbarrier.init.shared::cta.b64 [%0], %1;" ::"r"(bar), "r"(cnt)); }
__device__ __forceinline__ void mbar_expect(uint32_t bar, int bytes) { asm volatile("mbarrier.arrive.expect_tx.shared::cta.b64 _, [%0], %1;" ::"r"(bar), "r"(bytes) : "memory"); }
__device__ __forceinline__ void mbar_arrive(uint32_t bar) { asm volatile("mbarrier.arrive.shared::cta.b64 _, [%0];" ::"r"(bar) : "memory"); }
__device__ __forceinline__ void mbar_arrive_cl(uint32_t bar, uint32_t cta) {
  asm volatile("{\n.reg .b32 r;\nmapa.shared::cluster.u32 r, %0, %1;\nmbarrier.arrive.shared::cluster.b64 _, [r];\n}\n" ::"r"(bar), "r"(cta) : "memory");
}
__device__ __forceinline__ void mbar_wait(uint32_t bar, uint32_t parity) {
  asm volatile("{\n.reg .pred p;\n.reg .u32 n;\nmov.u32 n, 0;\n"
               "W_%=:\nmbarrier.try_wait.parity.shared::cta.b64 p, [%0], %1;\n@p bra D_%=;\n"
               "add.u32 n, n, 1;\nsetp.lt.u32 p, n, %2;\n@p bra W_%=;\ntrap;\nD_%=:\n}\n" ::"r"(bar), "r"(parity), "n"(SPIN_LIMIT) : "memory");
}
__device__ __forceinline__ void fence_async() { asm volatile("fence.proxy.async.shared::cta;" ::: "memory"); }
__device__ __forceinline__ void bar_sync(int id) { asm volatile("bar.sync %0, 128;" ::"r"(id) : "memory"); }
__device__ __forceinline__ void tma2d(uint32_t dst, const CUtensorMap* m, int c0, int c1, uint32_t bar) {
  asm volatile("cp.async.bulk.tensor.2d.shared::cluster.global.mbarrier::complete_tx::bytes [%0], [%1, {%3, %4}], [%2];"
               ::"r"(dst), "l"(m), "r"(bar), "r"(c0), "r"(c1) : "memory");
}
__device__ __forceinline__ void tma2d_mc(uint32_t dst, const CUtensorMap* m, int c0, int c1, uint32_t bar) {
  asm volatile("cp.async.bulk.tensor.2d.shared::cluster.global.mbarrier::complete_tx::bytes.multicast::cluster [%0], [%1, {%3, %4}], [%2], %5;"
               ::"r"(dst), "l"(m), "r"(bar), "r"(c0), "r"(c1), "h"((uint16_t)3) : "memory");
}
__device__ __forceinline__ void tma3d(uint32_t dst, const CUtensorMap* m, int c0, int c1, int c2, uint32_t bar) {
  asm volatile("cp.async.bulk.tensor.3d.shared::cluster.global.mbarrier::complete_tx::bytes [%0], [%1, {%3, %4, %5}], [%2];"
               ::"r"(dst), "l"(m), "r"(bar), "r"(c0), "r"(c1), "r"(c2) : "memory");
}
__device__ __forceinline__ void tma4d(uint32_t dst, const CUtensorMap* m, int c0, int c1, int c2, int c3, uint32_t bar) {
  asm volatile("cp.async.bulk.tensor.4d.shared::cluster.global.mbarrier::complete_tx::bytes [%0], [%1, {%3, %4, %5, %6}], [%2];"
               ::"r"(dst), "l"(m), "r"(bar), "r"(c0), "r"(c1), "r"(c2), "r"(c3) : "memory");
}
__device__ __forceinline__ void bulk_ld(uint32_t dst, const void* src, int bytes, uint32_t bar) {
  asm volatile("cp.async.bulk.shared::cluster.global.mbarrier::complete_tx::bytes [%0], [%1], %2, [%3];" ::"r"(dst), "l"(src), "r"(bytes), "r"(bar) : "memory");
}
__device__ __forceinline__ void bulk_ld_mc(uint32_t dst, const void* src, int bytes, uint32_t bar) {
  asm volatile("cp.async.bulk.shared::cluster.global.mbarrier::complete_tx::bytes.multicast::cluster [%0], [%1], %2, [%3], %4;"
               ::"r"(dst), "l"(src), "r"(bytes), "r"(bar), "h"((uint16_t)3) : "memory");
}
__device__ __forceinline__ void tma2d_st(const CUtensorMap* m, uint32_t src, int c0, int c1) {
  asm volatile("cp.async.bulk.tensor.2d.global.shared::cta.bulk_group [%0, {%2, %3}], [%1];" ::"l"(m), "r"(src), "r"(c0), "r"(c1) : "memory");
}
__device__ __forceinline__ void pf_l2(const void* p, int bytes) { asm volatile("cp.async.bulk.prefetch.L2.global [%0], %1;" ::"l"(p), "r"(bytes) : "memory"); }
__device__ __forceinline__ void pf_t2d(const CUtensorMap* m, int c0, int c1) {
  asm volatile("cp.async.bulk.prefetch.tensor.2d.L2.global [%0, {%1, %2}];" ::"l"(m), "r"(c0), "r"(c1) : "memory");
}
__device__ __forceinline__ void pf_t3d(const CUtensorMap* m, int c0, int c1, int c2) {
  asm volatile("cp.async.bulk.prefetch.tensor.3d.L2.global [%0, {%1, %2, %3}];" ::"l"(m), "r"(c0), "r"(c1), "r"(c2) : "memory");
}
__device__ __forceinline__ void ldsm4(uint32_t (&r)[4], uint32_t a) {
  asm volatile("ldmatrix.sync.aligned.m8n8.x4.shared.b16 {%0,%1,%2,%3}, [%4];" : "=r"(r[0]), "=r"(r[1]), "=r"(r[2]), "=r"(r[3]) : "r"(a) : "memory");
}
__device__ __forceinline__ void ldsm4t(uint32_t (&r)[4], uint32_t a) {
  asm volatile("ldmatrix.sync.aligned.m8n8.x4.trans.shared.b16 {%0,%1,%2,%3}, [%4];" : "=r"(r[0]), "=r"(r[1]), "=r"(r[2]), "=r"(r[3]) : "r"(a) : "memory");
}
__device__ __forceinline__ void stsm4(uint32_t a, uint32_t r0, uint32_t r1, uint32_t r2, uint32_t r3) {
  asm volatile("stmatrix.sync.aligned.m8n8.x4.shared.b16 [%0], {%1,%2,%3,%4};" ::"r"(a), "r"(r0), "r"(r1), "r"(r2), "r"(r3) : "memory");
}
__device__ __forceinline__ uint32_t pk2(float lo, float hi) { uint32_t r; asm("cvt.rn.bf16x2.f32 %0, %1, %2;" : "=r"(r) : "f"(hi), "f"(lo)); return r; }
__device__ __forceinline__ uint32_t hmul(uint32_t a, uint32_t b) { uint32_t r; asm("mul.rn.bf16x2 %0, %1, %2;" : "=r"(r) : "r"(a), "r"(b)); return r; }
__device__ __forceinline__ uint32_t hadd(uint32_t a, uint32_t b) { uint32_t r; asm("add.rn.bf16x2 %0, %1, %2;" : "=r"(r) : "r"(a), "r"(b)); return r; }
__device__ __forceinline__ uint32_t hmax(uint32_t a, uint32_t b) { uint32_t r; asm("max.bf16x2 %0, %1, %2;" : "=r"(r) : "r"(a), "r"(b)); return r; }
__device__ __forceinline__ uint32_t hmin(uint32_t a, uint32_t b) { uint32_t r; asm("min.bf16x2 %0, %1, %2;" : "=r"(r) : "r"(a), "r"(b)); return r; }
__device__ __forceinline__ uint32_t hmaxabs(uint32_t a, uint32_t b) { uint32_t r; asm("max.xorsign.abs.bf16x2 %0, %1, %2;" : "=r"(r) : "r"(a), "r"(b)); return r; }
__device__ __forceinline__ float ex2(float x) { float r; asm("ex2.approx.ftz.f32 %0, %1;" : "=f"(r) : "f"(x)); return r; }
__device__ __forceinline__ float rcp_fast(float x) { float r; asm("rcp.approx.ftz.f32 %0, %1;" : "=f"(r) : "f"(x)); return r; }
__device__ __forceinline__ uint32_t phi2(float lo, float hi) {
  uint32_t t;
  asm("cvt.rn.relu.bf16x2.f32 %0, %1, %2;" : "=r"(t) : "f"(hi), "f"(lo));
  const uint32_t e = pk2(ex2(lo * 1.4426950408889634f), ex2(hi * 1.4426950408889634f));
  return hadd(hadd(t, hmin(e, 0x3F803F80u)), 0x35863586u);
}
__device__ __forceinline__ bool opaque_true() { uint32_t v; asm volatile("mov.u32 %0, %%nctaid.y;" : "=r"(v)); return v != 0; }
__device__ __forceinline__ int norm_exp(uint32_t (&v)[32], float f0) {
  uint32_t m[4] = {hmaxabs(__float_as_uint(f0) >> 16, v[0]), v[1], v[2], v[3]};
#pragma unroll
  for (int i = 4; i < 32; i++) m[i & 3] = hmaxabs(m[i & 3], v[i]);
  m[0] = hmaxabs(hmaxabs(m[0], m[1]), hmaxabs(m[2], m[3]));
  const int e = min(max((int)(__reduce_max_sync(~0u, max(m[0] & 0x7FFFu, (m[0] >> 16) & 0x7FFFu)) >> 7), 1), 253);
  if (e > 141) {
#pragma unroll
    for (int i = 0; i < 32; i++) v[i] = hmul(v[i], 0x07000700u);
  }
  return e;
}
template <int I0, int I1>
__device__ __forceinline__ void norm_cvt(uint32_t (&v)[32], float f0, int e) {
  const uint32_t sc = (e > 141 ? 255 - e : 142 - e) * 0x00800080u;
#pragma unroll
  for (int i = I0; i < I1; i++) {
    const uint32_t a = hmul(v[i], sc);
    v[i] = (a & 0x0FFF0FFFu) * 7 + a;
  }
  if (I0 == 0) v[0] = __byte_perm(v[0], __half_as_ushort(__float2half_rn(f0 * __uint_as_float((254 - e) << 23))), 0x3254);
}
__device__ __forceinline__ void poll_ge(const unsigned* p, unsigned target) {
#pragma unroll 1
  for (int n = 0; n < SPIN_LIMIT; n++) {
    unsigned v;
    asm volatile("ld.relaxed.gpu.global.u32 %0, [%1];" : "=r"(v) : "l"(p) : "memory");
    if (__all_sync(~0u, (int)(v - target) >= 0)) { asm volatile("fence.acquire.gpu;" ::: "memory"); return; }
  }
  __trap();
}

__device__ __forceinline__ bool elect_one() {
  uint32_t p;
  asm volatile("{\n.reg .pred p;\nelect.sync _|p, 0xffffffff;\nselp.u32 %0, 1, 0, p;\n}\n" : "=r"(p));
  return p;
}
__device__ __forceinline__ uint4 ld_nc4(const void* p) {
  uint4 v;
  asm volatile("ld.global.nc.L1::no_allocate.v4.u32 {%0,%1,%2,%3}, [%4];" : "=r"(v.x), "=r"(v.y), "=r"(v.z), "=r"(v.w) : "l"(p));
  return v;
}
__device__ __forceinline__ void st_cg4(void* p, uint4 v) {
  asm volatile("st.global.cg.v4.u32 [%0], {%1,%2,%3,%4};" ::"l"(p), "r"(v.x), "r"(v.y), "r"(v.z), "r"(v.w) : "memory");
}
__device__ __forceinline__ uint32_t mapa(uint32_t a, uint32_t cta) { uint32_t r; asm("mapa.shared::cluster.u32 %0, %1, %2;" : "=r"(r) : "r"(a), "r"(cta)); return r; }
__device__ __forceinline__ void st_async(uint32_t a, uint32_t v, uint32_t bar) {
  asm volatile("st.async.weak.shared::cluster.mbarrier::complete_tx::bytes.b32 [%0], %1, [%2];" ::"r"(a), "r"(v), "r"(bar) : "memory");
}
__device__ __forceinline__ void st_async4(uint32_t a, uint32_t x, uint32_t y, uint32_t z, uint32_t w, uint32_t bar) {
  asm volatile("st.async.weak.shared::cluster.mbarrier::complete_tx::bytes.v4.b32 [%0], {%1,%2,%3,%4}, [%5];" ::"r"(a), "r"(x), "r"(y), "r"(z), "r"(w), "r"(bar) : "memory");
}
__device__ __forceinline__ void tma3d_st(const CUtensorMap* m, uint32_t src, int c0, int c1, int c2) {
  asm volatile("cp.async.bulk.tensor.3d.global.shared::cta.bulk_group [%0, {%2, %3, %4}], [%1];" ::"l"(m), "r"(src), "r"(c0), "r"(c1), "r"(c2) : "memory");
}
__device__ __forceinline__ uint4 ld_rlx4(const void* p) {
  uint4 v;
  asm volatile("{\n.reg .b128 t;\n.reg .b64 a, b;\nld.relaxed.gpu.global.b128 t, [%4];\nmov.b128 {a, b}, t;\nmov.b64 {%0, %1}, a;\nmov.b64 {%2, %3}, b;\n}\n"
               : "=r"(v.x), "=r"(v.y), "=r"(v.z), "=r"(v.w) : "l"(p) : "memory");
  return v;
}
__device__ __forceinline__ void ld_stale4(uint4& v, const void* p, uint32_t tag) {
  asm volatile("{\n.reg .b128 t;\n.reg .b64 a, b;\n.reg .b32 x;\n.reg .pred p;\n"
               "lop3.b32 x, %0, %5, 1, 0x28;\nsetp.ne.u32 p, x, 0;\n"
               "mov.b64 a, {%0, %1};\nmov.b64 b, {%2, %3};\nmov.b128 t, {a, b};\n"
               "@p ld.relaxed.gpu.global.b128 t, [%4];\n"
               "mov.b128 {a, b}, t;\nmov.b64 {%0, %1}, a;\nmov.b64 {%2, %3}, b;\n}\n"
               : "+r"(v.x), "+r"(v.y), "+r"(v.z), "+r"(v.w) : "l"(p), "r"(tag) : "memory");
}
__device__ __forceinline__ void st_tag4(void* p, float a, float b, float c, float d, uint32_t tag) {
  asm volatile("{\n.reg .b128 t;\n.reg .b64 a, b;\nmov.b64 a, {%1, %2};\nmov.b64 b, {%3, %4};\nmov.b128 t, {a, b};\nst.relaxed.gpu.global.b128 [%0], t;\n}\n"
               ::"l"(p), "r"((__float_as_uint(a) & ~1u) | tag), "f"(b), "f"(c), "f"(d) : "memory");
}
__device__ __forceinline__ uint32_t stale8(const uint4 (&f)[8], uint32_t tag) {
  uint32_t r[4];
#pragma unroll
  for (int i = 0; i < 4; i++) asm("lop3.b32 %0, %1, %2, %3, 0x7E;" : "=r"(r[i]) : "r"(f[2 * i].x), "r"(f[2 * i + 1].x), "r"(tag));
  asm("lop3.b32 %0, %0, %1, %2, 0xFE;" : "+r"(r[0]) : "r"(r[1]), "r"(r[2]));
  return r[0] | r[3];
}

struct ConvC { uint32_t a1[2][4], wa[2], wb[2], sg; };
__device__ __forceinline__ uint64_t dsc(uint32_t lo, uint32_t hi) { return ((uint64_t)hi << 32) | lo; }
__device__ __forceinline__ uint32_t hfma(uint32_t a, uint32_t b, uint32_t c) { uint32_t r; asm("fma.rn.f16x2 %0, %1, %2, %3;" : "=r"(r) : "r"(a), "r"(b), "r"(c)); return r; }
__device__ __forceinline__ uint32_t hfnma(uint32_t a, uint32_t b, uint32_t c) { uint32_t r; asm("{.reg .b32 n; neg.f16x2 n, %1; fma.rn.f16x2 %0, n, %2, %3;}" : "=r"(r) : "r"(a), "r"(b), "r"(c)); return r; }
__device__ __forceinline__ uint32_t hmul16(uint32_t a, uint32_t b) { uint32_t r; asm("mul.rn.f16x2 %0, %1, %2;" : "=r"(r) : "r"(a), "r"(b)); return r; }
template <int N> __device__ __forceinline__ void keepu(uint32_t (&d)[N]) {
#pragma unroll
  for (int i = 0; i < N; i++) asm volatile("" : "+r"(d[i])::"memory");
}
__device__ __forceinline__ void conv_m1(const ConvC& K, uint32_t (&u)[16], uint32_t l) {
  wg_fence();
  wgmma_hrs_n64<1>(u, K.a1[0][0], K.a1[0][1], K.a1[0][2], K.a1[0][3], dsc(l, 32), 0);
  wgmma_hrs_n64<1>(u, K.a1[1][0], K.a1[1][1], K.a1[1][2], K.a1[1][3], dsc(l + 16, 32), 1);
  wg_commit();
}
__device__ __forceinline__ void conv_s2(const ConvC& K, uint32_t (&u)[16], uint32_t (&Z)[2][8], uint32_t dfl) {
  uint32_t fr[8], fi[8];
#pragma unroll
  for (int c = 0; c < 8; c++) {
    const uint32_t r = hfma(K.wa[c & 1], u[2 * c + 1], u[2 * c]);
    fi[c] = hfma(K.wb[c & 1], r, u[2 * c + 1]);
    fr[c] = hfma(K.wa[c & 1], fi[c], r);
  }
  wg_fence();
#pragma unroll
  for (int p = 0; p < 2; p++) {
    wgmma_hrs_n32<0>(Z[p], fr[4 * p], fr[4 * p + 2], fr[4 * p + 1], fr[4 * p + 3], dsc(dfl, 32), 0);
    wgmma_hrs_n32<0>(Z[p], fi[4 * p], fi[4 * p + 2], fi[4 * p + 1], fi[4 * p + 3], dsc(dfl + 16, 32), 1);
  }
  wg_commit();
}
__device__ __forceinline__ void conv_win(const ConvC& K, const uint32_t (&X)[2][8], uint32_t (&W)[2][8]) {
#pragma unroll
  for (int b = 0; b < 4; b++)
#pragma unroll
    for (int c = 0; c < 2; c++) {
      const uint32_t xr = X[b >> 1][2 * c + (b & 1)], xi = X[b >> 1][4 + 2 * c + (b & 1)];
      const int a = b ? b - 1 : 0;
      W[b >> 1][2 * c + (b & 1)] = b ? hfnma(K.sg, X[a >> 1][4 + 2 * c + (a & 1)], xr) : hmul16(xr, 0x3C003C00u);
      W[b >> 1][4 + 2 * c + (b & 1)] = b ? hfma(K.sg, X[a >> 1][2 * c + (a & 1)], xi) : hmul16(xi, 0x3C003C00u);
    }
}
template <int p>
__device__ __forceinline__ void conv_pw(uint32_t (&X)[2][8], uint32_t (&H)[2][8], uint32_t (&V)[8], uint32_t dil) {
  uint32_t pr[2][2], pi[2][2];
#pragma unroll
  for (int jj = 0; jj < 2; jj++)
#pragma unroll
    for (int c = 0; c < 2; c++) {
      const int j = 2 * p + jj;
      uint32_t sr = 0, si = 0;
#pragma unroll
      for (int a = 0; a <= j; a++) {
        const int b = j - a;
        const uint32_t hr = H[a >> 1][2 * c + (a & 1)], hi = H[a >> 1][4 + 2 * c + (a & 1)];
        const uint32_t xr = X[b >> 1][2 * c + (b & 1)], xi = X[b >> 1][4 + 2 * c + (b & 1)];
        sr = a == 0 ? hmul16(hr, xr) : hfma(hr, xr, sr);
        si = a == 0 ? hmul16(hr, xi) : hfma(hr, xi, si);
        sr = hfnma(hi, xi, sr);
        si = hfma(hi, xr, si);
      }
      pr[jj][c] = sr; pi[jj][c] = si;
    }
  wg_fence();
  wgmma_hrs_n32<0>(V, pr[0][0], pr[1][0], pr[0][1], pr[1][1], dsc(dil, 32), 0);
  wgmma_hrs_n32<0>(V, pi[0][0], pi[1][0], pi[0][1], pi[1][1], dsc(dil + 16, 32), 1);
  wg_commit();
}
template <int p>
__device__ __forceinline__ void conv_it(const ConvC& K, uint32_t (&V)[8], uint32_t vst) {
#pragma unroll
  for (int jj = 0; jj < 2; jj++) {
    uint32_t wr[2], wi[2];
#pragma unroll
    for (int c = 0; c < 2; c++) {
      const uint32_t r = hfnma(K.wa[c], V[4 + 2 * c + jj], V[2 * c + jj]);
      wi[c] = hfnma(K.wb[c], r, V[4 + 2 * c + jj]);
      wr[c] = hfnma(K.wa[c], wi[c], r);
    }
    stsm4(vst + (2 * p + jj) * 2048, wr[0], wr[1], wi[0], wi[1]);
  }
}
__device__ __forceinline__ void conv_m4(uint32_t (&y)[8], uint32_t (&a)[4][4], uint32_t d4l) {
  wg_fence();
  wgmma_hrs_n32<0>(y, a[0][0], a[0][1], a[0][2], a[0][3], dsc(d4l, 64), 0);
#pragma unroll
  for (int s = 1; s < 4; s++) wgmma_hrs_n32<0>(y, a[s][0], a[s][1], a[s][2], a[s][3], dsc(d4l + s * 16, 64), 1);
  wg_commit();
}

struct Params {
  CUtensorMap tmX, tmW, tmWo, tmWo1, tmK, tmV, tmQ, tmOA, tmOB;
  const __nv_bfloat16 *shift_k, *h, *D, *x, *w, *wo, *q;
  float *part, *kv;
  uint4* o;
  unsigned *ocnt, *epoch;
  const uint32_t *thr, *img;
};

__global__ void __cluster_dims__(2, 1, 1) __launch_bounds__(384, 1) fused_kernel(const __grid_constant__ Params P) {
  extern __shared__ __align__(1024) uint8_t smem[];
  const uint32_t sb = __shfl_sync(~0u, smem_u32(smem), 0);
  const uint32_t bars = sb + OFF_BAR;
  const int tid = threadIdx.x, lane = tid & 31;
  const int warp = __shfl_sync(~0u, tid >> 5, 0);
  const int rank = blockIdx.x & 1, cl = blockIdx.x >> 1;
  const int mb = cl < 4 ? 4 + cl : cl < 36 ? (cl - 4) >> 3 : 4 + (cl - 36) / 7;
  const int hb = (cl - 36) % 7;
  const int hq = cl < 4 ? A0COL : cl < 36 ? (cl - 4) & 7 : hb + (hb >= A0COL);
  const int hp = 2 * hq + rank;
  const int rb = 2 * mb + (hq >> 2), cb = hq & 3;
#define BAR(i) (bars + 8 * (i))

  if (tid == 0) { STAMP(0, 0); GSTAMP(0, 30); }
  if (warp == 8) {
    if (elect_one()) {
      mbar_init(BAR(B_FULL1), 1);
      asm volatile("fence.mbarrier_init.release.cluster;" ::: "memory");
      mbar_expect(BAR(B_FULL1), STAGE_BYTES);
      tma3d(sb + 32768, &P.tmW, hp * 64, 0, 0, BAR(B_FULL1));
    }
    if (lane == 0) STAMP(3, 21);
  } else if (lane == 0) {
    const int wi = warp - (warp > 8);
#pragma unroll
    for (int r = 0; r < 6; r++)
      if (r < 5 || wi < B_COUNT - 56) mbar_init(BAR(1 + 11 * r + wi), ((uint32_t)(bar_counts(r) >> (4 * wi)) & 15) + 1);
    asm volatile("fence.mbarrier_init.release.cluster;" ::: "memory");
  }
  if (tid == 0) STAMP(2, 6);
  asm volatile("barrier.cluster.arrive.relaxed.aligned;\nbarrier.cluster.wait.aligned;" ::: "memory");
  if (warp == 8 && elect_one()) tma2d_mc(sb + rank * 16384, &P.tmX, 0, mb * 256 + rank * 128, BAR(B_FULL1));
  if (tid == 256) STAMP(2, 7);

  if (warp < 8) {
    asm volatile("setmaxnreg.inc.sync.aligned.u32 224;");
    const int wg = warp >> 2, w = warp & 3, g = lane >> 2, q = lane & 3, t = tid & 127;
    const bool elect = (t == 0);
    const uint32_t s16 = (sb & 0x3FFFF) >> 4;
    uint32_t pq[2][16];
    ConvC K;
    {
      float acc[2][96];
      int st = 0, ph = 0;
#pragma unroll 1
      for (int kb = 0; kb < 14; kb++) {
        mbar_wait(BAR(B_FULL1 + st), ph);
        if (kb == 0 && elect) { STAMP(wg, 1); GSTAMP(wg, 26); }
        if (kb == 8 && elect) { STAMP(wg, 16); GSTAMP(wg, 25); }
        const uint32_t da = s16 + st * (STAGE_BYTES >> 4) + wg * 1024 + (1 << 16);
        const uint32_t db = s16 + st * (STAGE_BYTES >> 4) + 2048 + (512 << 16);
        wg_fence();
#pragma unroll
        for (int ks = 0; ks < 4; ks++) {
          wgmma_ss_n192<0, 1>(acc[0], dsc(da + ks * 2, SW128), dsc(db + ks * 128, SW128), (kb | ks) != 0);
          wgmma_ss_n192<0, 1>(acc[1], dsc(da + 512 + ks * 2, SW128), dsc(db + ks * 128, SW128), (kb | ks) != 0);
        }
        wg_commit();
        wg_wait<1>();
        if (kb > 0 && t < 2) mbar_arrive_cl(BAR(B_EMPTY1 + (st == 0 ? 2 : st - 1)), t);
        if (++st == 3) { st = 0; ph ^= 1; }
      }
#define TAIL_MMA(mt, stage) do { wg_fence(); _Pragma("unroll") for (int ks = 0; ks < 4; ks++) \
        wgmma_ss_n192<0, 1>(acc[mt], dsc(s16 + (stage) * (STAGE_BYTES >> 4) + wg * 1024 + (mt) * 512 + (1 << 16) + ks * 2, SW128), \
                            dsc(s16 + (stage) * (STAGE_BYTES >> 4) + 2048 + (512 << 16) + ks * 128, SW128), 1); wg_commit(); } while (0)
      mbar_wait(BAR(B_FULL1 + 2), 0);
      TAIL_MMA(0, 2);
      wg_wait<1>();
      if (elect) mbar_arrive(BAR(B_SFREE));
      mbar_wait(BAR(B_FULL1 + 0), 1);
      TAIL_MMA(0, 0);
      TAIL_MMA(1, 2);
      const uint32_t lrow = sb + wg * 16384 + (16 * w + 8 * ((lane >> 3) & 1) + (lane & 7)) * 128 + (((lane >> 4) ^ (lane & 7)) << 4);
#define E1K(mt, i) do { if (opaque_true()) { _Pragma("unroll") for (int j = (i); j < (i) + 2; j++) { \
          const float* a = &acc[mt][32 + 8 * j]; const float* b = a + 32; const uint32_t o = (lrow ^ (j * 32)) + (mt) * 8192; \
          stsm4(o + 2 * STAGE_BYTES, pk2(b[0], b[1]), pk2(b[2], b[3]), pk2(b[4], b[5]), pk2(b[6], b[7])); \
          stsm4(o, phi2(a[0], a[1]), phi2(a[2], a[3]), phi2(a[4], a[5]), phi2(a[6], a[7])); } } } while (0)
#define E1Q(mt) do { if (opaque_true()) { _Pragma("unroll") for (int i = 0; i < 16; i++) pq[mt][i] = phi2(acc[mt][2 * i], acc[mt][2 * i + 1]); } } while (0)
#define PK_READY(mt) do { fence_async(); __syncwarp(); if (lane == 0) mbar_arrive(BAR(B_PKRDY + (mt))); } while (0)
      wg_wait<1>();
      keep(acc[0]);
      if (elect) STAMP(wg, 18);
      E1K(0, 0);
      TAIL_MMA(1, 0);
      E1K(0, 2);
      if (elect) STAMP(wg, 19);
      PK_READY(0);
      wg_wait<0>();
      keep(acc[1]);
      asm volatile("setmaxnreg.dec.sync.aligned.u32 200;");
      if (elect) { STAMP(wg, 2); GSTAMP(wg, 27); }
      E1K(1, 0);
      E1K(1, 2);
      PK_READY(1);
      if (elect) STAMP(wg, 3);
      {
        const uint4* ct = (const uint4*)P.thr + t;
#pragma unroll
        for (int s = 0; s < 2; s++) { const uint4 u = ld_nc4(ct + s * 128); K.a1[s][0] = u.x; K.a1[s][1] = u.y; K.a1[s][2] = u.z; K.a1[s][3] = u.w; }
        const uint4 u = ld_nc4(ct + 2 * 128);
        K.wa[0] = u.x; K.wa[1] = u.y; K.wb[0] = u.z; K.wb[1] = u.w;
        K.sg = (lane & 4) ? 0xBC00BC00u : 0x3C003C00u;
      }
      if (CWAIT) mbar_wait(BAR(B_PKFREE), 0);
      if (elect) STAMP(wg, 4);
      E1Q(0);
      E1Q(1);
    }
    if (elect) STAMP(wg, 17);
    mbar_wait(BAR(B_H), 0);
    mbar_wait(BAR(B_PKRDY + 1), 0);
    if (elect) STAMP(wg, 5);
    {
      const uint32_t dfl = s16 + (OFF_F2F >> 4) + (8 << 16), dil = s16 + (OFF_F2I >> 4) + (8 << 16), d4l = s16 + (OFF_F4 >> 4) + (8 << 16);
      const uint32_t xl = s16 + (OFF_XT >> 4) + 4 * wg * (XT_STRIDE >> 4) + (8 << 16);
      const uint32_t hl = s16 + (OFF_H >> 4) + wg * 512 + (8 << 16);
      uint32_t vst = sb + wg * 8192 + w * 512 + lane * 16, vld = sb + wg * 8192 + w * 2048 + lane * 16;
      uint32_t ya = mapa(sb + OFF_XT + 4 * wg * XT_STRIDE + (2 * rank + (w & 1)) * 1024 + lane * 16, w >> 1);
      const uint32_t ybar = mapa(BAR(B_Y), w >> 1);
      asm volatile("" : "+r"(vst), "+r"(vld), "+r"(ya));
      uint32_t ux[16], uh[16], W[2][8], V0[8], V1[8], y[8], a[4][4];
      uint4* const ot = P.o + ((2 * mb + wg) * 16 + hq) * 1024 + (16 * w + g) * 8 + ((4 * rank + q) ^ g);
#define YOUT(i) do { if ((w >> 1) == rank) { \
          asm volatile("st.shared.v4.b32 [%0], {%1,%2,%3,%4};" ::"r"(ya + (i) * XT_STRIDE), "r"(y[0]), "r"(y[2]), "r"(y[4]), "r"(y[6]) : "memory"); \
          asm volatile("st.shared.v4.b32 [%0], {%1,%2,%3,%4};" ::"r"(ya + (i) * XT_STRIDE + 512), "r"(y[1]), "r"(y[3]), "r"(y[5]), "r"(y[7]) : "memory"); \
        } else { \
          mbar_wait(BAR(B_XFREE + 4 * wg + (i)), 0); \
          st_async4(ya + (i) * XT_STRIDE, y[0], y[2], y[4], y[6], ybar); \
          st_async4(ya + (i) * XT_STRIDE + 512, y[1], y[3], y[5], y[7], ybar); } } while (0)
      auto ocalc = [&](const int hh) {
        if (hh == 0) {
          if (elect) STAMP(wg, 8);
          mbar_wait(BAR(B_KV), 0);
          if (elect) STAMP(wg, 9);
        }
        float oa[2][20];
        wg_fence();
#pragma unroll
        for (int m = 0; m < 4; m++) {
          const uint32_t* p = &pq[m & 1][8 * hh + 4 * (m >> 1)];
          wgmma_rs_n40<1>(oa[m & 1], p[0], p[1], p[2], p[3], dsc(s16 + (OFF_KVB >> 4) + hh * 160 + (m >> 1) * 16 + (8 << 16), 32), m >> 1);
        }
        wg_commit();
        wg_wait<0>();
#pragma unroll
        for (int mt = 0; mt < 2; mt++) {
          float (&o)[20] = oa[mt];
          keep(o);
          const uint32_t den = hadd(pk2(o[16], o[18]), 0x35863586u);
#pragma unroll
          for (int r = 0; r < 2; r++) {
            const float ri = rcp_fast(__uint_as_float(r ? (den & 0xFFFF0000u) : (den << 16)));
            uint4 u;
            u.x = pk2(o[2 * r] * ri, o[2 * r + 1] * ri);
            u.y = pk2(o[4 + 2 * r] * ri, o[5 + 2 * r] * ri);
            u.z = pk2(o[8 + 2 * r] * ri, o[9 + 2 * r] * ri);
            u.w = pk2(o[12 + 2 * r] * ri, o[13 + 2 * r] * ri);
            st_cg4(ot + hh * 8 * 1024 + (64 * mt + 8 * r) * 8, u);
          }
        }
        __syncwarp();
        if (lane == 0) mbar_arrive(BAR(hh ? B_ODONE1 : B_ODONE));
        if (hh == 0 && elect) STAMP(wg, 10);
      };
      uint32_t X[4][2][8], H[4][2][8];
      conv_m1(K, ux, xl);
      conv_m1(K, uh, hl);
      wg_wait<1>(); keepu(ux);
      if (lane == 0) mbar_arrive_cl(BAR(B_XFREE + 4 * wg), rank ^ 1);
      conv_s2(K, ux, X[0], dfl);
      wg_wait<1>(); keepu(uh);
      conv_s2(K, uh, H[0], dfl);
#pragma unroll
      for (int i = 0; i < 4; i++) {
        const bool nx = i < 3;
        const int n = nx ? i + 1 : i;
        const uint32_t vo = (i & 1) ? OFF_H + (i >> 1) * 16384 : OFF_VP;
        if (2 * i == OCH) ocalc(0);
        if (2 * i == OCH + O1D) ocalc(1);
        if (nx) {
          if (n == 2) mbar_wait(BAR(B_H2), 0);
          conv_m1(K, ux, xl + n * (XT_STRIDE >> 4));
          conv_m1(K, uh, hl + (n >> 1) * 1024 + (n & 1) * 256);
        }
        if (2 * i != OCH && 2 * i != OCH + O1D) { if (nx) { if (i > 0) wg_wait<3>(); else wg_wait<2>(); } else wg_wait<1>(); }
        keepu(X[i][0]); keepu(X[i][1]); keepu(H[i][0]); keepu(H[i][1]);
        conv_win(K, X[i], W);
        conv_pw<0>(W, H[i], V0, dil);
        conv_pw<1>(W, H[i], V1, dil);
        wg_wait<2>();
        if (i > 0) { keepu(y); YOUT(i - 1); }
        if (2 * i + 1 == OCH) ocalc(0);
        if (2 * i + 1 == OCH + O1D) ocalc(1);
        if (nx) {
          keepu(ux); keepu(uh);
          if (lane == 0) mbar_arrive_cl(BAR(B_XFREE + 4 * wg + n), rank ^ 1);
          conv_s2(K, ux, X[n], dfl);
          wg_wait<1>();
        } else wg_wait<0>();
        keepu(V0); keepu(V1);
        conv_it<0>(K, V0, vst + vo);
        conv_it<1>(K, V1, vst + vo);
        bar_sync(1 + wg);
#pragma unroll
        for (int s = 0; s < 4; s++) ldsm4t(a[s], vld + vo + s * 512);
        if (nx) conv_s2(K, uh, H[n], dfl);
        conv_m4(y, a, d4l);
        if (i > 0 && lane < 2) mbar_arrive_cl(BAR(B_AFREE + i - 1), lane);
        if (elect && i < 3) STAMP(wg, i < 2 ? 6 + i : 9 + i);
      }
      wg_wait<0>(); keepu(y);
      YOUT(3);
      __syncwarp();
      if (lane == 0) mbar_arrive(BAR(B_Y));
      if (elect) STAMP(wg, 12);
    }
    {
      float acc[64];
#define G2_MMA(da, db, first) do { wg_fence(); _Pragma("unroll") for (int ks = 0; ks < 4; ks++) \
        wgmma_ss_n128<0, 1>(acc, dsc((da) + ks * 2, SW128), dsc((db) + ks * 128, SW128), ks || !(first)); wg_commit(); } while (0)
      const uint32_t a0 = s16 + wg * 512 + (1 << 16), b0 = s16 + (512 << 16);
      uint64_t ta = SLOT_A, tb = SLOT_B;
      uint32_t da = a0 + (SLOT_A & 15) * 1024, db = b0 + (SLOT_B & 15) * 1024, fb = BAR(B_FULL2);
      uint32_t cons = mapa(BAR(B_CONS2 - 1), t & 1);
      const bool rel = __shfl_sync(~0u, t, lane) < 2;
#pragma unroll 1
      for (int kb = 0; kb < HOLD2; kb++) {
        if (G2S == 0 && tid == 128) STAMP(2, 8 + kb);
        mbar_wait(fb, 0);
        if (G2S == 1 && tid == 128) STAMP(2, 8 + kb);
        if (kb == 0 && elect) { STAMP(wg, 13); GSTAMP(wg, 28); }
        G2_MMA(da, db, kb == 0);
        ta >>= 4; tb >>= 4;
        da = a0 + ((uint32_t)ta & 15) * 1024; db = b0 + ((uint32_t)tb & 15) * 1024; fb += 8;
        asm volatile("" : "+r"(da), "+r"(db));
        wg_wait<1>();
        if (kb > 0 && kb < 12 && rel) asm volatile("mbarrier.arrive.shared::cluster.b64 _, [%0];" ::"r"(cons) : "memory");
        cons += 8;
      }
      if (HOLD2 == 11) { wg_wait<0>(); if (rel) asm volatile("mbarrier.arrive.shared::cluster.b64 _, [%0];" ::"r"(cons) : "memory"); }
#pragma unroll
      for (int kb = HOLD2; kb < 16; kb++) {
        if (wg == 1) mbar_wait(BAR(B_FULL2 + kb), 0);
        else if (kb == HOLD2) asm volatile("bar.sync 3, 256;" ::: "memory");
        G2_MMA(a0 + ((SLOT_A >> (4 * kb)) & 15) * 1024, b0 + ((SLOT_B >> (4 * kb)) & 15) * 1024, false);
      }
      if (wg == 1) asm volatile("bar.arrive 3, 256;" ::: "memory");
      const uint32_t stg = sb + wg * 8192 + w * 2048, so0 = ((SLOT_A >> 56) & 15) * 16384, so1 = ((SLOT_A >> 60) & 15) * 16384;
      const uint32_t lrow = stg + (8 * ((lane >> 3) & 1) + (lane & 7)) * 128 + (((lane >> 4) ^ (lane & 7)) << 4);
      const int col = 1024 + 256 * cb + 128 * rank, row = 128 * rb + 64 * wg + 16 * w;
      wg_wait<0>();
      keep(acc);
      if (elect) { STAMP(wg, 14); GSTAMP(wg, 29); }
#pragma unroll
      for (int cp = 0; cp < 8; cp++) {
        const float* a = &acc[8 * cp];
        stsm4((lrow ^ ((cp & 3) * 32)) + (cp >> 2 ? so1 : so0), pk2(a[0], a[1]), pk2(a[2], a[3]), pk2(a[4], a[5]), pk2(a[6], a[7]));
        if (cp == 7 || (EPI2 && cp == 3)) {
          fence_async();
          __syncwarp();
          if (elect_one()) {
            if (cp == 3 || !EPI2) tma2d_st(&P.tmOB, stg + so0, col, row);
            if (cp == 7) tma2d_st(&P.tmOB, stg + so1, col + 64, row);
          }
        }
      }
      asm volatile("cp.async.bulk.commit_group;\ncp.async.bulk.wait_group.read 0;" ::: "memory");
      if (elect) {
        STAMP(wg, 15); GSTAMP(wg, 31); PDUMP(wg); if (wg == 0) PDUMP(2);
      }
    }
  } else {
    asm volatile("setmaxnreg.dec.sync.aligned.u32 56;");
    const int hw = warp - 9, g = lane >> 2, q = lane & 3;
#define sbar (bars + 8 * (B_STG - 18) + 16 * warp)
    if (warp == 8) {
      int st = 1, pp = 1;
      const uint8_t* pfx = (const uint8_t*)P.x + (mb * 256 + hp * 16 + (lane & 15)) * 2048;
      const uint8_t* pfw = (const uint8_t*)P.w + (mb * 8 + (lane & 7)) * 6144 + (lane >> 3) * 2048 + hp * 128;
#pragma unroll 1
      for (int kb = 1; kb < 16; kb++) {
        if (kb >= 3) mbar_wait(BAR(B_EMPTY1 + st), pp);
        const uint32_t sa = sb + st * STAGE_BYTES;
        if (elect_one()) {
          mbar_expect(BAR(B_FULL1 + st), STAGE_BYTES);
          tma2d_mc(sa + rank * 16384, &P.tmX, kb * 64, mb * 256 + rank * 128, BAR(B_FULL1 + st));
          tma3d(sa + 32768, &P.tmW, hp * 64, kb * 64, 0, BAR(B_FULL1 + st));
        }
        if (kb == 1 && lane == 0) STAMP(2, 24);
        if (PFD && kb >= 2) {
#pragma unroll 1
          for (int j = kb == 2 ? 3 : kb + PFD; j <= kb + PFD && j < 16; j++) {
            if (lane < 16) asm volatile("prefetch.global.L2 [%0];" ::"l"(pfx + j * 128));
            if (lane < 24) asm volatile("prefetch.global.L2 [%0];" ::"l"(pfw + j * (64 * 6144)));
          }
          if (kb >= QPF && kb < QPF + 8) asm volatile("prefetch.global.L2 [%0];" ::"l"((const uint8_t*)P.q + (blockIdx.x * 256 + (kb - QPF) * 32 + lane) * 128));
          if (kb >= 4)
            asm volatile("prefetch.global.L2 [%0];" ::"l"(kb < 12 ? (const uint8_t*)P.h + (blockIdx.x * 256 + (kb - 4) * 32 + lane) * 128
                                                                  : (const uint8_t*)P.wo + (blockIdx.x * 128 + (kb - 12) * 32 + lane) * 128));
        }
        if (++st == 3) { st = 0; pp ^= 1; }
      }
      if (lane == 0) STAMP(2, 1);
    } else {
      {
        const uint32_t clk0 = __shfl_sync(~0u, (uint32_t)clock(), 0), stg = sb + OFF_STG + hw * STG_STRIDE;
        const unsigned epoch = __shfl_sync(~0u, P.epoch[blockIdx.x], 0);
        const uint32_t tag = ~epoch & 1;
        uint32_t tap[2][4];
#pragma unroll
        for (int cg = 0; cg < 2; cg++) {
          const uint2 u = __ldg((const uint2*)(P.shift_k + (16 * cl + 8 * cg + g) * 4));
          tap[cg][0] = __byte_perm(u.x, 0, 0x1010); tap[cg][1] = __byte_perm(u.x, 0, 0x3232);
          tap[cg][2] = __byte_perm(u.y, 0, 0x1010); tap[cg][3] = __byte_perm(u.y, 0, 0x3232);
        }
        if (hw == 0 && lane < 8) *(float*)(smem + OFF_D + 4 * lane) = __bfloat162float(P.D[blockIdx.x * 8 + lane]);
        if (hw == 1) asm volatile("prefetch.global.L2 [%0];" ::"l"(P.thr + (lane + 32 * (blockIdx.x & 1)) * 32));
        if (hw == 0 && elect_one()) {
          *(volatile unsigned*)(smem + OFF_EPOCH) = epoch;
          mbar_expect(BAR(B_XRAW), 16384);
          mbar_expect(BAR(B_Y), 16384 + 64);
        }
        for (int i = hw * 32 + lane; i < 528; i += 96) st_tag4(P.part + (hp * 8 + mb) * 2176 + 4 * i, 0.f, 0.f, 0.f, 0.f, tag ^ 1);
        if (hw < 2 || lane < 2) st_tag4(P.kv + hp * 2176 + (4 * (hw < 2 ? 64 * mb + 32 * hw + lane : 512 + 2 * mb + lane)), 0.f, 0.f, 0.f, 0.f, tag ^ 1);
        if (lane == 0) STAMP(3, hw);
        const uint32_t xo = sb + OFF_XT + g * XT_STRIDE + rank * 2048 + q * 4;
        const int krow = 8 + (lane & 7) - (lane >> 3);
        const uint32_t ka = stg + krow * 32 + ((krow & 4) << 2), va = stg + 2304 + lane * 32 + ((lane & 4) << 2);
        int ph = 0, b = 0;
#pragma unroll 1
        for (int ci = hw - 3; ci < 16; ci += 3) {
          const uint32_t bo = b ? OFF_F2F - OFF_STG : 0, bn = b ? 0 : OFF_F2F - OFF_STG;
          if (ci + 3 < 16) {
            while (__any_sync(~0u, (uint32_t)clock() - clk0 < HSTART + (ci + 3) * PACE)) __nanosleep(64);
            if (elect_one()) {
              mbar_expect(sbar + 8 * (b ^ 1), 2304 + 2048);
              tma2d(stg + bn, &P.tmK, 16 * cl, 1024 * rank + 64 * (ci + 3) - 8, sbar + 8 * (b ^ 1));
              tma2d(stg + bn + 2304, &P.tmV, 16 * cl, 1024 * rank + 64 * (ci + 3), sbar + 8 * (b ^ 1));
            }
          }
          if (ci >= 0) {
            mbar_wait(sbar + 8 * b, (ph >> b) & 1);
            ph ^= 1 << b;
#pragma unroll 1
            for (int grp = 0; grp < 2; grp++) {
#pragma unroll
              for (int cg = 0; cg < 2; cg++) {
                const uint32_t dst = mapa(xo + (ci >> 3) * 1024 + ((ci & 7) * 4 + 2 * grp) * 16, cg), xbar = mapa(BAR(B_XRAW), cg);
                uint32_t vv[4], kk[4][4];
                ldsm4t(vv, (va ^ (cg * 16)) + bo + grp * 1024);
#pragma unroll
                for (int rg = 0; rg < 4; rg++) ldsm4t(kk[rg], (ka ^ (cg * 16)) + bo + grp * 1024 + rg * 256);
#pragma unroll
                for (int rg = 0; rg < 4; rg++)
                  vv[rg] = hmul(hadd(hadd(hadd(hmul(kk[rg][3], tap[cg][3]), hmul(kk[rg][2], tap[cg][2])), hmul(kk[rg][1], tap[cg][1])), hmul(kk[rg][0], tap[cg][0])), vv[rg]);
                if (cg == rank) {
#pragma unroll
                  for (int rg = 0; rg < 4; rg++) asm volatile("st.shared.b32 [%0], %1;" ::"r"(dst + (rg & 1) * 512 + (rg >> 1) * 16), "r"(vv[rg]) : "memory");
                } else {
#pragma unroll
                  for (int rg = 0; rg < 4; rg++) st_async(dst + (rg & 1) * 512 + (rg >> 1) * 16, vv[rg], xbar);
                }
              }
            }
          }
          b ^= 1;
        }
      }
      if (lane == 0) STAMP(3, 3 + hw);
      asm volatile("bar.sync 4, 96;" ::: "memory");
      if (hw == 0 && elect_one()) { mbar_expect(BAR(B_XT), 10240); bulk_ld(sb + OFF_F2F, P.img, 10240, BAR(B_XT)); }
      mbar_wait(BAR(B_XRAW), 0);
    }
#pragma unroll 1
    for (int n = hw < 0 ? 3 : 0; n < 4; n++) {
      const bool isH = n >= 3;
      const int c = isH ? (warp & 1) + 2 * (warp & 2) : hw + 3 * n;
      if (c < 8) {
        int ln;
        asm volatile("mov.u32 %0, %%laneid;" : "=r"(ln));
        uint8_t* dst = smem + (isH ? OFF_H + (c & 2) * 8192 + (c >> 2) * 8192 + (c & 1) * 4096 : OFF_XT + c * XT_STRIDE) + ((ln >> 4) * 512 + (ln & 15) * 16);
        const uint8_t* src0 = isH ? (const uint8_t*)P.h + (blockIdx.x * 8 + c) * 4096 + ((ln & 15) * 32 + (ln & 16)) : dst;
        const uint8_t* src1 = src0 + (isH ? 512 : 256);
        uint32_t v[32];
#pragma unroll
        for (int i = 0; i < 8; i++) {
          const uint4 u = *(const uint4*)(((i & 1) ? src1 : src0) + (i >> 1) * 1024);
          v[4 * i] = u.x; v[4 * i + 1] = u.y; v[4 * i + 2] = u.z; v[4 * i + 3] = u.w;
        }
        if (isH) mbar_wait(BAR(B_XT), 0);
        const float f0 = __uint_as_float(v[0] << 16) + ((isH && ln == 0) ? *(const float*)(smem + OFF_D + 4 * c) : 0.f);
        const int e = norm_exp(v, f0);
        norm_cvt<0, 32>(v, f0, e);
        if (isH) {
          if (ln < 2) st_async(mapa(sb + OFF_SCALE + (8 * rank + c) * 4, ln), min(max(e + smem[OFF_EX + c] - 124, 1), 254) << 23, mapa(BAR(B_Y), ln));
          mbar_wait(BAR(B_SFREE), 0);
        } else if (ln == 0) smem[OFF_EX + c] = e;
#pragma unroll
        for (int i = 0; i < 8; i++)
          *(uint4*)(dst + (i >> 1) * 1024 + (i & 1) * 256) = make_uint4(v[4 * i], v[4 * i + 1], v[4 * i + 2], v[4 * i + 3]);
        if (n < 2 && elect_one()) {
          if (n == 0) mbar_expect(sbar, 4096);
          tma3d(sb + OFF_STG + 2048 * c, &P.tmQ, 16 * cl, 64 * rank, 2 * c, sbar);
        }
      }
      if (n >= 2) {
        fence_async();
        __syncwarp();
        if (lane == 0) { mbar_arrive(BAR(isH ? B_H : B_XT)); STAMP(3, (isH ? 17 : 13) + hw); }
      }
    }
#define SLOT(tab, kb) (sb + ((uint32_t)((tab) >> (4 * (kb))) & 15) * 16384)
#define LOAD_B(kb) tma4d(SLOT(SLOT_B, kb), &P.tmWo, 0, ((kb) >> 3) * 32, 2 * ((kb) & 7), 4 * cb + 2 * rank, BAR(B_FULL2 + (kb)))
#define LOAD_A(kb) bulk_ld_mc(SLOT(SLOT_A, kb) + rank * 8192, P.o + (rb * 16 + (kb)) * 1024 + rank * 512, 8192, BAR(B_FULL2 + (kb)))
    asm volatile("setmaxnreg.inc.sync.aligned.u32 104;");
    const unsigned epoch = *(volatile unsigned*)(smem + OFF_EPOCH);
    const uint32_t tag = ~epoch & 1;
    const int pi = hw < 2 ? 64 * mb - 288 + tid : 512 + 2 * mb + (lane & 1);
    const float* psrc = P.part + hp * 8 * 2176 + 4 * pi;
    uint4 f[8];
    {
      const uint32_t s16 = (sb & 0x3FFFF) >> 4;
      const int t = tid & 127, c = 2 + (warp & 1) + 2 * (warp & 2);
      uint32_t v[32];
      const uint4* hp4 = (const uint4*)(P.h + (blockIdx.x * 8 + c) * 2048) + ((lane & 15) * 2 + (lane >> 4));
#pragma unroll
      for (int i = 0; i < 8; i++) { const uint4 u = ld_nc4(hp4 + i * 32); v[4 * i] = u.x; v[4 * i + 1] = u.y; v[4 * i + 2] = u.z; v[4 * i + 3] = u.w; }
      float kva[36];
#pragma unroll
      for (int mt = 0; mt < 2; mt++) {
        mbar_wait(BAR(B_PKRDY + mt), 0);
        wg_fence();
#pragma unroll
        for (int ks = 0; ks < 8; ks++) {
          const uint32_t o = (ks >> 2) * 1024 + mt * 512 + (ks & 3) * 128, vb = (2 * STAGE_BYTES >> 4) + o;
          wgmma_ss_n72<1, 1>(kva, dsc(s16 + o + (1 << 16), SW128), dsc(s16 + vb + (((OFF_ONES >> 4) - vb) << 16), SW128), (mt | ks) != 0);
        }
        wg_commit();
      }
      float* pdst = P.part + (hp * 8 + mb) * 2176 + t * 4;
      float* zdst = P.part + (hp * 8 + mb) * 2176 + 2048 + (t >> 1);
      asm volatile("" : "+l"(pdst), "+l"(zdst));
      wg_wait<0>();
      keep(kva);
      if (hw < 1) {
#pragma unroll
        for (int c = 0; c < 4; c++) st_tag4(pdst + c * 512, kva[4 * c], kva[4 * c + 1], kva[4 * c + 2], kva[4 * c + 3], tag);
      } else {
#pragma unroll
        for (int c = 4; c < 8; c++) st_tag4(pdst + (c - 4) * 512, kva[4 * c], kva[4 * c + 1], kva[4 * c + 2], kva[4 * c + 3], tag);
      }
      const float z2 = __shfl_down_sync(~0u, kva[32], 4), z3 = __shfl_down_sync(~0u, kva[34], 4);
      if (!(lane & 7)) st_tag4(zdst, kva[32], kva[34], z2, z3, tag);
      if (lane == 0) mbar_arrive(BAR(B_PKFREE));
      if (hw == 0 && lane == 0) STAMP(3, 24);
      const float f0 = __uint_as_float(v[0] << 16) + (lane == 0 ? *(const float*)(smem + OFF_D + 4 * c) : 0.f);
      const int e = norm_exp(v, f0);
      if (HSPL > 0) norm_cvt<0, HSPL>(v, f0, e);
      if (hw >= 0) {
        if (hw == 0 && lane == 0) STAMP(3, 20);
#pragma unroll
        for (int p = 0; p < 8; p++) f[p] = ld_rlx4(psrc + p * 2176);
      }
      if (HSPL < 32) norm_cvt<HSPL, 32>(v, f0, e);
      uint8_t* dst = smem + OFF_H + 16384 + (warp & 3) * 4096 + (lane >> 4) * 512 + (lane & 15) * 16;
#pragma unroll
      for (int i = 0; i < 8; i++)
        *(uint4*)(dst + (i >> 1) * 1024 + (i & 1) * 256) = make_uint4(v[4 * i], v[4 * i + 1], v[4 * i + 2], v[4 * i + 3]);
      if (lane < 2) st_async(mapa(sb + OFF_SCALE + (8 * rank + c) * 4, lane), min(max(e + smem[OFF_EX + c] - 124, 1), 254) << 23, mapa(BAR(B_Y), lane));
      fence_async();
      __syncwarp();
      if (lane == 0) mbar_arrive(BAR(B_H2));
    }
    if (warp == 8) {
      mbar_wait(BAR(B_PKFREE), 0);
      {
        const uint32_t c0 = clock();
#pragma unroll 1
        for (int i = 0; i < 14; i++) {
          const int kb = i >> 1;
          while (__any_sync(~0u, (uint32_t)clock() - c0 < i * BPACE)) __nanosleep(32);
          if (elect_one()) {
            if (!(i & 1)) mbar_expect(BAR(B_FULL2 + kb), 16384);
            tma4d(SLOT(SLOT_B, kb) + (i & 1) * 8192, &P.tmWo1, 0, 0, 2 * kb, 4 * cb + 2 * rank + (i & 1), BAR(B_FULL2 + kb));
            if (i == 0) mbar_expect(BAR(B_Q), 8192);
            if (i < 4) tma3d(sb + OFF_SPARE + 2048 * i, &P.tmQ, 16 * cl, 64 * rank + 32 * (i >> 1), 2 * ((i + 6) & 7), BAR(B_Q));
          }
        }
      }
      if (lane == 0) STAMP(2, 2);
      mbar_wait(BAR(B_AFREE), 0);
      if (elect_one()) mbar_expect(BAR(B_FULL2), 16384);
      {
        const uint32_t dst = SLOT(SLOT_A, 0) + rank * 8192;
        const uint4* src = P.o + rb * 16 * 1024 + rank * 512;
        poll_ge(&P.ocnt[rb * 32], 16 * (epoch + 1));
        asm volatile("fence.proxy.async.global;" ::: "memory");
        if (lane == 0) STAMP(2, 3);
        if (elect_one()) bulk_ld_mc(dst, src, 8192, BAR(B_FULL2));
        if (lane == 0) STAMP(3, 23);
      }
#pragma unroll 1
      for (int kb = 1; kb < 7; kb++) {
        mbar_wait(BAR(kb < 3 ? B_AFREE + kb : B_CONS2 + ((kb - 3) >> 1)), 0);
        if (elect_one()) { mbar_expect(BAR(B_FULL2 + kb), 16384); LOAD_A(kb); }
      }
#pragma unroll 1
      for (int kb = 7; kb < 16; kb++) {
        mbar_wait(BAR(B_CONS2 + kb - 5), 0);
        if (kb == 8) mbar_wait(BAR(B_O1RDY), 0);
        if (elect_one()) { mbar_expect(BAR(B_FULL2 + kb), 32768); LOAD_A(kb); LOAD_B(kb); }
      }
      if (lane == 0) { P.epoch[blockIdx.x] = epoch + 1; STAMP(2, 5); }
    } else {
      {
#pragma unroll 1
        for (int n = 0; __any_sync(~0u, stale8(f, tag) & 1); n++) {
#pragma unroll
          for (int p = 0; p < 8; p++) ld_stale4(f[p], psrc + p * 2176, tag);
          if (n > SPIN_LIMIT) __trap();
        }
        float s0 = 0.f, s1 = 0.f, s2 = 0.f, s3 = 0.f;
#pragma unroll
        for (int p = 0; p < 8; p++) { s0 += __uint_as_float(f[p].x); s1 += __uint_as_float(f[p].y); s2 += __uint_as_float(f[p].z); s3 += __uint_as_float(f[p].w); }
        if (hw < 2 || lane < 2) st_tag4(P.kv + hp * 2176 + (4 * pi), s0, s1, s2, s3, tag);
      }
      if (lane == 0 && hw == 0) STAMP(3, 8);
      if (hw == 2) {
        unsigned* cnt = P.ocnt + (2 * mb + lane) * 32;
#pragma unroll 1
        for (int hh = 0; hh < 2; hh++) {
          mbar_wait(BAR(hh ? B_ODONE1 : B_ODONE), 0);
          if (lane < 2) asm volatile("red.release.gpu.global.add.u32 [%0], 1;" ::"l"(cnt + hh * 512) : "memory");
          if (lane == 0) STAMP(3, hh ? 6 : 7);
        }
        poll_ge(&P.ocnt[512 + rb * 32], 16 * (epoch + 1));
        asm volatile("fence.proxy.async.global;" ::: "memory");
        if (lane == 0) { mbar_arrive(BAR(B_O1RDY)); STAMP(2, 4); }
        __syncwarp();
      } else {
        if (PD2) __nanosleep(PD2);
        const int t = tid - 288;
        const float* src = P.kv + hp * 2176 + (4 * t);
        const float* zsrc = P.kv + hp * 2176 + (2048 + (t & 48) + 2 * (lane & 6));
        uint4 zp = ld_rlx4(zsrc);
#pragma unroll
        for (int p = 0; p < 8; p++) f[p] = ld_rlx4(src + 4 * ((p & 3) * 128 + (p >> 2) * 64));
        if (!opaque_true()) __trap();
#pragma unroll 1
        for (int n = 0; __any_sync(~0u, (stale8(f, tag) | (zp.x ^ tag)) & 1); n++) {
          ld_stale4(zp, zsrc, tag);
#pragma unroll
          for (int p = 0; p < 8; p++) ld_stale4(f[p], src + 4 * ((p & 3) * 128 + (p >> 2) * 64), tag);
          if (n > SPIN_LIMIT) __trap();
        }
#define PK2U(a, b) pk2(__uint_as_float(a), __uint_as_float(b))
        const uint32_t zf = (lane & 1) ? ((lane & 8) ? zp.w : zp.z) : ((lane & 8) ? zp.y : zp.x);
        const uint32_t zz = PK2U(zf, zf);
        *(uint4*)(smem + OFF_KVB + hw * 2560 + 2048 + lane * 16) = make_uint4(zz, zz, zz, zz);
        if (!opaque_true()) __trap();
#pragma unroll
        for (int hh = 0; hh < 2; hh++) {
          const uint4* ff = &f[4 * hh];
          uint8_t* dst = smem + OFF_KVB + hh * 2560 + q * 512 + (16 * hw + g) * 16;
          *(uint4*)dst = make_uint4(PK2U(ff[0].x, ff[0].y), PK2U(ff[1].x, ff[1].y), PK2U(ff[2].x, ff[2].y), PK2U(ff[3].x, ff[3].y));
          *(uint4*)(dst + 128) = make_uint4(PK2U(ff[0].z, ff[0].w), PK2U(ff[1].z, ff[1].w), PK2U(ff[2].z, ff[2].w), PK2U(ff[3].z, ff[3].w));
        }
        fence_async();
        __syncwarp();
        if (lane == 0) { mbar_arrive(BAR(B_KV)); if (hw == 0) STAMP(3, 9); }
      }
#define QBUF(ci) (sb + 2048 * (ci) + ((ci) < 6 ? OFF_STG : (ci) < 10 ? OFF_SPARE - 6 * 2048 : OFF_F2F - 10 * 2048))
      mbar_wait(BAR(B_Y), 0);
      if (elect_one()) {
        mbar_expect(sbar + 8, 4096);
#pragma unroll 1
        for (int ci = hw ? hw + 9 : 12; ci < 16; ci += 3) tma3d(QBUF(ci), &P.tmQ, 16 * cl, 64 * rank + 32, 2 * (ci & 7), sbar + 8);
      }
      mbar_wait(BAR(B_Q), 0);
      mbar_wait(sbar, hw == 0);
      {
        const float2 sc0 = *(const float2*)(smem + OFF_SCALE + 8 * q), sc1 = *(const float2*)(smem + OFF_SCALE + 32 + 8 * q);
        const uint32_t yl = sb + OFF_XT + (lane & 7) * XT_STRIDE + (lane >> 3) * 16;
#pragma unroll 1
        for (int ci = hw; ci < 16; ci += 3) {
          const uint32_t qb = QBUF(ci);
          if (ci >= 10) mbar_wait(sbar + 8, 1);
#pragma unroll 1
          for (int nl = 0; nl < 2; nl++) {
            uint32_t yy[2][4], qq[2][4];
            const uint32_t qa = qb + lane * 32 + ((lane & 4) << 2) + nl * 1024;
#pragma unroll
            for (int cg = 0; cg < 2; cg++) { ldsm4t(yy[cg], yl + cg * 2048 + (2 * ci + nl) * 64); ldsm4(qq[cg], qa ^ (cg * 16)); }
#pragma unroll
            for (int cg = 0; cg < 2; cg++) {
              const float2 sc = cg ? sc1 : sc0;
#pragma unroll
              for (int m = 0; m < 4; m++) {
                const float2 f = __half22float2(*(const __half2*)&yy[cg][m]);
                qq[cg][m] = hmul(qq[cg][m], pk2(f.x * sc.x, f.y * sc.y));
              }
              stsm4(qa ^ (cg * 16), qq[cg][0], qq[cg][1], qq[cg][2], qq[cg][3]);
            }
          }
          fence_async();
          __syncwarp();
          if (elect_one()) tma3d_st(&P.tmOA, qb, 16 * cl, 64 * rank + 32 * (ci >> 3), 2 * (ci & 7));
        }
        asm volatile("cp.async.bulk.commit_group;\ncp.async.bulk.wait_group.read 0;" ::: "memory");
      }
      if (lane == 0) STAMP(3, 10 + hw);
    }
  }
}

typedef CUresult (*EncodeFn)(CUtensorMap*, CUtensorMapDataType, cuuint32_t, void*, const cuuint64_t*, const cuuint64_t*,
                             const cuuint32_t*, const cuuint32_t*, CUtensorMapInterleave, CUtensorMapSwizzle,
                             CUtensorMapL2promotion, CUtensorMapFloatOOBfill);

static void enc(EncodeFn fn, CUtensorMap* m, const void* p, int rank, const cuuint64_t* dims, const cuuint64_t* strides,
                const cuuint32_t* box, CUtensorMapSwizzle swz, CUtensorMapL2promotion promo) {
  cuuint32_t es[4] = {1, 1, 1, 1};
  fn(m, CU_TENSOR_MAP_DATA_TYPE_BFLOAT16, rank, (void*)p, dims, strides, box, es, CU_TENSOR_MAP_INTERLEAVE_NONE, swz, promo,
     CU_TENSOR_MAP_FLOAT_OOB_FILL_NONE);
}

extern "C" void kernel_launch(void* const* d_in, const int* in_sizes, int n_in, void* d_out, int out_size) {
  void* fp = nullptr;
  cudaDriverEntryPointQueryResult qr;
  cudaGetDriverEntryPoint("cuTensorMapEncodeTiled", &fp, cudaEnableDefault, &qr);
  EncodeFn fn = (EncodeFn)fp;
  Params P;
  P.shift_k = (const __nv_bfloat16*)d_in[3]; P.h = (const __nv_bfloat16*)d_in[4]; P.D = (const __nv_bfloat16*)d_in[5];
  P.q = (const __nv_bfloat16*)d_in[0];
  cudaGetSymbolAddress((void**)&P.part, g_part); cudaGetSymbolAddress((void**)&P.kv, g_kv); cudaGetSymbolAddress((void**)&P.o, g_o);
  cudaGetSymbolAddress((void**)&P.ocnt, g_ocnt); cudaGetSymbolAddress((void**)&P.epoch, g_epoch);
  cudaGetSymbolAddress((void**)&P.thr, c_thr); cudaGetSymbolAddress((void**)&P.img, c_img);
  P.x = (const __nv_bfloat16*)d_in[6]; P.w = (const __nv_bfloat16*)d_in[7]; P.wo = (const __nv_bfloat16*)d_in[8];
  const CUtensorMapSwizzle S128 = CU_TENSOR_MAP_SWIZZLE_128B, S32 = CU_TENSOR_MAP_SWIZZLE_32B;
  const CUtensorMapL2promotion P0 = CU_TENSOR_MAP_L2_PROMOTION_NONE, P128 = CU_TENSOR_MAP_L2_PROMOTION_L2_128B;
  { cuuint64_t d[2] = {1024, 2048}, s[1] = {2048}; cuuint32_t b[2] = {64, 128}; enc(fn, &P.tmX, d_in[6], 2, d, s, b, S128, P128); }
  { cuuint64_t d[3] = {1024, 1024, 3}, s[2] = {6144, 2048}; cuuint32_t b[3] = {64, 64, 3}; enc(fn, &P.tmW, d_in[7], 3, d, s, b, S128, P128); }
  { cuuint64_t d[4] = {64, 64, 16, 16}, s[3] = {2048, 131072, 128}; cuuint32_t b[4] = {64, 32, 2, 2}; enc(fn, &P.tmWo, d_in[8], 4, d, s, b, S128, P128); }
  { cuuint64_t d[4] = {64, 64, 16, 16}, s[3] = {2048, 131072, 128}; cuuint32_t b[4] = {64, 32, 2, 1}; enc(fn, &P.tmWo1, d_in[8], 4, d, s, b, S128, P128); }
  { cuuint64_t d[2] = {1024, 2048}, s[1] = {2048}; cuuint32_t b[2] = {16, 72}; enc(fn, &P.tmK, d_in[1], 2, d, s, b, S32, PKV); }
  { cuuint64_t d[2] = {1024, 2048}, s[1] = {2048}; cuuint32_t b[2] = {16, 64}; enc(fn, &P.tmV, d_in[2], 2, d, s, b, S32, PKV); }
  { cuuint64_t d[3] = {1024, 128, 16}, s[2] = {32768, 2048}; cuuint32_t b[3] = {16, 32, 2}; enc(fn, &P.tmQ, d_in[0], 3, d, s, b, S32, PKV); }
  { cuuint64_t d[3] = {1024, 128, 16}, s[2] = {65536, 4096}; cuuint32_t b[3] = {16, 32, 2}; enc(fn, &P.tmOA, d_out, 3, d, s, b, S32, P0); }
  { cuuint64_t d[2] = {2048, 2048}, s[1] = {4096}; cuuint32_t b[2] = {64, 16}; enc(fn, &P.tmOB, d_out, 2, d, s, b, S128, P0); }
  cudaFuncSetAttribute(fused_kernel, cudaFuncAttributeMaxDynamicSharedMemorySize, SMEM_TOTAL);
  fused_kernel<<<128, 384, SMEM_TOTAL>>>(P);
}
```

```cpp
#include <cuda_runtime.h>
#include <cuda_bf16.h>
#include <cuda_fp16.h>
#include <cuda.h>
#include <stdint.h>

template<int TA, int TB, int SA=1> __device__ __forceinline__ void wgmma_ss_n192(float (&d)[96], uint64_t da, uint64_t db, int scale_d) {
  asm volatile("{\n.reg .pred p;\nsetp.ne.b32 p, %98, 0;\n"
    "wgmma.mma_async.sync.aligned.m64n192k16.f32.bf16.bf16 {%0, %1, %2, %3, %4, %5, %6, %7, %8, %9, %10, %11, %12, %13, %14, %15, %16, %17, %18, %19, %20, %21, %22, %23, %24, %25, %26, %27, %28, %29, %30, %31, %32, %33, %34, %35, %36, %37, %38, %39, %40, %41, %42, %43, %44, %45, %46, %47, %48, %49, %50, %51, %52, %53, %54, %55, %56, %57, %58, %59, %60, %61, %62, %63, %64, %65, %66, %67, %68, %69, %70, %71, %72, %73, %74, %75, %76, %77, %78, %79, %80, %81, %82, %83, %84, %85, %86, %87, %88, %89, %90, %91, %92, %93, %94, %95}, %96, %97, p, %101, 1, %99, %100;\n}\n"
    : "+f"(d[0]), "+f"(d[1]), "+f"(d[2]), "+f"(d[3]), "+f"(d[4]), "+f"(d[5]), "+f"(d[6]), "+f"(d[7]), "+f"(d[8]), "+f"(d[9]), "+f"(d[10]), "+f"(d[11]), "+f"(d[12]), "+f"(d[13]), "+f"(d[14]), "+f"(d[15]), "+f"(d[16]), "+f"(d[17]), "+f"(d[18]), "+f"(d[19]), "+f"(d[20]), "+f"(d[21]), "+f"(d[22]), "+f"(d[23]), "+f"(d[24]), "+f"(d[25]), "+f"(d[26]), "+f"(d[27]), "+f"(d[28]), "+f"(d[29]), "+f"(d[30]), "+f"(d[31]), "+f"(d[32]), "+f"(d[33]), "+f"(d[34]), "+f"(d[35]), "+f"(d[36]), "+f"(d[37]), "+f"(d[38]), "+f"(d[39]), "+f"(d[40]), "+f"(d[41]), "+f"(d[42]), "+f"(d[43]), "+f"(d[44]), "+f"(d[45]), "+f"(d[46]), "+f"(d[47]), "+f"(d[48]), "+f"(d[49]), "+f"(d[50]), "+f"(d[51]), "+f"(d[52]), "+f"(d[53]), "+f"(d[54]), "+f"(d[55]), "+f"(d[56]), "+f"(d[57]), "+f"(d[58]), "+f"(d[59]), "+f"(d[60]), "+f"(d[61]), "+f"(d[62]), "+f"(d[63]), "+f"(d[64]), "+f"(d[65]), "+f"(d[66]), "+f"(d[67]), "+f"(d[68]), "+f"(d[69]), "+f"(d[70]), "+f"(d[71]), "+f"(d[72]), "+f"(d[73]), "+f"(d[74]), "+f"(d[75]), "+f"(d[76]), "+f"(d[77]), "+f"(d[78]), "+f"(d[79]), "+f"(d[80]), "+f"(d[81]), "+f"(d[82]), "+f"(d[83]), "+f"(d[84]), "+f"(d[85]), "+f"(d[86]), "+f"(d[87]), "+f"(d[88]), "+f"(d[89]), "+f"(d[90]), "+f"(d[91]), "+f"(d[92]), "+f"(d[93]), "+f"(d[94]), "+f"(d[95])
    : "l"(da), "l"(db), "r"(scale_d), "n"(TA), "n"(TB), "n"(SA));
}
template<int TA, int TB, int SA=1> __device__ __forceinline__ void wgmma_ss_n128(float (&d)[64], uint64_t da, uint64_t db, int scale_d) {
  asm volatile("{\n.reg .pred p;\nsetp.ne.b32 p, %66, 0;\n"
    "wgmma.mma_async.sync.aligned.m64n128k16.f32.bf16.bf16 {%0, %1, %2, %3, %4, %5, %6, %7, %8, %9, %10, %11, %12, %13, %14, %15, %16, %17, %18, %19, %20, %21, %22, %23, %24, %25, %26, %27, %28, %29, %30, %31, %32, %33, %34, %35, %36, %37, %38, %39, %40, %41, %42, %43, %44, %45, %46, %47, %48, %49, %50, %51, %52, %53, %54, %55, %56, %57, %58, %59, %60, %61, %62, %63}, %64, %65, p, %69, 1, %67, %68;\n}\n"
    : "+f"(d[0]), "+f"(d[1]), "+f"(d[2]), "+f"(d[3]), "+f"(d[4]), "+f"(d[5]), "+f"(d[6]), "+f"(d[7]), "+f"(d[8]), "+f"(d[9]), "+f"(d[10]), "+f"(d[11]), "+f"(d[12]), "+f"(d[13]), "+f"(d[14]), "+f"(d[15]), "+f"(d[16]), "+f"(d[17]), "+f"(d[18]), "+f"(d[19]), "+f"(d[20]), "+f"(d[21]), "+f"(d[22]), "+f"(d[23]), "+f"(d[24]), "+f"(d[25]), "+f"(d[26]), "+f"(d[27]), "+f"(d[28]), "+f"(d[29]), "+f"(d[30]), "+f"(d[31]), "+f"(d[32]), "+f"(d[33]), "+f"(d[34]), "+f"(d[35]), "+f"(d[36]), "+f"(d[37]), "+f"(d[38]), "+f"(d[39]), "+f"(d[40]), "+f"(d[41]), "+f"(d[42]), "+f"(d[43]), "+f"(d[44]), "+f"(d[45]), "+f"(d[46]), "+f"(d[47]), "+f"(d[48]), "+f"(d[49]), "+f"(d[50]), "+f"(d[51]), "+f"(d[52]), "+f"(d[53]), "+f"(d[54]), "+f"(d[55]), "+f"(d[56]), "+f"(d[57]), "+f"(d[58]), "+f"(d[59]), "+f"(d[60]), "+f"(d[61]), "+f"(d[62]), "+f"(d[63])
    : "l"(da), "l"(db), "r"(scale_d), "n"(TA), "n"(TB), "n"(SA));
}
template<int TA, int TB, int SA=1> __device__ __forceinline__ void wgmma_ss_n72(float (&d)[36], uint64_t da, uint64_t db, int scale_d) {
  asm volatile("{\n.reg .pred p;\nsetp.ne.b32 p, %38, 0;\n"
    "wgmma.mma_async.sync.aligned.m64n72k16.f32.bf16.bf16 {%0, %1, %2, %3, %4, %5, %6, %7, %8, %9, %10, %11, %12, %13, %14, %15, %16, %17, %18, %19, %20, %21, %22, %23, %24, %25, %26, %27, %28, %29, %30, %31, %32, %33, %34, %35}, %36, %37, p, %41, 1, %39, %40;\n}\n"
    : "+f"(d[0]), "+f"(d[1]), "+f"(d[2]), "+f"(d[3]), "+f"(d[4]), "+f"(d[5]), "+f"(d[6]), "+f"(d[7]), "+f"(d[8]), "+f"(d[9]), "+f"(d[10]), "+f"(d[11]), "+f"(d[12]), "+f"(d[13]), "+f"(d[14]), "+f"(d[15]), "+f"(d[16]), "+f"(d[17]), "+f"(d[18]), "+f"(d[19]), "+f"(d[20]), "+f"(d[21]), "+f"(d[22]), "+f"(d[23]), "+f"(d[24]), "+f"(d[25]), "+f"(d[26]), "+f"(d[27]), "+f"(d[28]), "+f"(d[29]), "+f"(d[30]), "+f"(d[31]), "+f"(d[32]), "+f"(d[33]), "+f"(d[34]), "+f"(d[35])
    : "l"(da), "l"(db), "r"(scale_d), "n"(TA), "n"(TB), "n"(SA));
}
template<int TB, int SA=1> __device__ __forceinline__ void wgmma_rs_n40(float (&d)[20], uint32_t a0, uint32_t a1, uint32_t a2, uint32_t a3, uint64_t db, int scale_d) {
  asm volatile("{\n.reg .pred p;\nsetp.ne.b32 p, %25, 0;\n"
    "wgmma.mma_async.sync.aligned.m64n40k16.f32.bf16.bf16 {%0, %1, %2, %3, %4, %5, %6, %7, %8, %9, %10, %11, %12, %13, %14, %15, %16, %17, %18, %19}, {%20, %21, %22, %23}, %24, p, %27, 1, %26;\n}\n"
    : "+f"(d[0]), "+f"(d[1]), "+f"(d[2]), "+f"(d[3]), "+f"(d[4]), "+f"(d[5]), "+f"(d[6]), "+f"(d[7]), "+f"(d[8]), "+f"(d[9]), "+f"(d[10]), "+f"(d[11]), "+f"(d[12]), "+f"(d[13]), "+f"(d[14]), "+f"(d[15]), "+f"(d[16]), "+f"(d[17]), "+f"(d[18]), "+f"(d[19])
    : "r"(a0), "r"(a1), "r"(a2), "r"(a3), "l"(db), "r"(scale_d), "n"(TB), "n"(SA));
}
template<int TB> __device__ __forceinline__ void wgmma_hrs_n64(uint32_t (&d)[16], uint32_t a0, uint32_t a1, uint32_t a2, uint32_t a3, uint64_t db, int scale_d) {
  asm volatile("{\n.reg .pred p;\nsetp.ne.b32 p, %21, 0;\n"
    "wgmma.mma_async.sync.aligned.m64n64k16.f16.f16.f16 {%0, %1, %2, %3, %4, %5, %6, %7, %8, %9, %10, %11, %12, %13, %14, %15}, {%16, %17, %18, %19}, %20, p, 1, 1, %22;\n}\n"
    : "+r"(d[0]), "+r"(d[1]), "+r"(d[2]), "+r"(d[3]), "+r"(d[4]), "+r"(d[5]), "+r"(d[6]), "+r"(d[7]), "+r"(d[8]), "+r"(d[9]), "+r"(d[10]), "+r"(d[11]), "+r"(d[12]), "+r"(d[13]), "+r"(d[14]), "+r"(d[15])
    : "r"(a0), "r"(a1), "r"(a2), "r"(a3), "l"(db), "r"(scale_d), "n"(TB));
}
template<int TB> __device__ __forceinline__ void wgmma_hrs_n32(uint32_t (&d)[8], uint32_t a0, uint32_t a1, uint32_t a2, uint32_t a3, uint64_t db, int scale_d) {
  asm volatile("{\n.reg .pred p;\nsetp.ne.b32 p, %13, 0;\n"
    "wgmma.mma_async.sync.aligned.m64n32k16.f16.f16.f16 {%0, %1, %2, %3, %4, %5, %6, %7}, {%8, %9, %10, %11}, %12, p, 1, 1, %14;\n}\n"
    : "+r"(d[0]), "+r"(d[1]), "+r"(d[2]), "+r"(d[3]), "+r"(d[4]), "+r"(d[5]), "+r"(d[6]), "+r"(d[7])
    : "r"(a0), "r"(a1), "r"(a2), "r"(a3), "l"(db), "r"(scale_d), "n"(TB));
}

__device__ __align__(128) const uint32_t c_thr[1536] = {
  0x33fb33ff,0xa49c9de4,0x33273352,0xaf2cae76,0x33e233f1,0xa96ca7bd,0x32c432f7,0xb045afdd,0x33b733cf,0xac3eaaf7,0x3250328c,0xb0eab099,
  0x3378339a,0xadbcacff,0x31cd3211,0xb182b137,0x33d033fb,0xaadea46a,0x299e2d17,0xb3e0b396,0x32fb337a,0xafd2adb1,0xa78b1f76,0xb3f2b3ff,
  0x318b3254,0xb1c5b0e5,0xae6bac32,0xb354b3b8,0x2f4230a3,0xb321b285,0xb133b040,0xb215b2c7,0x337c33f2,0xada5a759,0xb179afc8,0xb1d6b2fe,
  0x31463293,0xb204b08e,0xb394b2ba,0xad23b055,0x2b402f4e,0xb3cbb31e,0xb3e4b3f9,0x293ba533,0xac269c52,0xb3bab400,0xb258b357,0x30e02e5f,
  0x330133e5,0xafbda922,0xb3f3b3c9,0x2727ab59,0x2deb314a,0xb36fb200,0xb194b32f,0x31bc2f0a,0xacdb2084,0xb39fb3ff,0xa565aea4,0x33f93347,
  0xb2b6b0db,0xb05ab25c,0x30892c1a,0x329733bc,0x326033d4,0xb0d6aa94,0xb00ab29b,0x32e83084,0x20e82f64,0xb3feb318,0x2d8da597,0x338133f8,
  0xb1fcae48,0xb14fb35c,0x339031b8,0x2d3a3199,0xb3e6b3ae,0x2909ac7b,0x32d133f4,0xb030a6f5,0x319d33bf,0xb1b3ac02,0x2e3ca874,0x335e33ec,
  0xacc32b89,0xb3a3b3c6,0x33f83276,0x25c930b7,0xb3dcb1f8,0xaa01b154,0x30653335,0xb2b0aef4,0xb107b383,0x32392d81,0xafa6214d,0xb307b3fe,
  0x30bc33a5,0xb273acb7,0x33c5311b,0x2ba23229,0xb0cc94b6,0xb267b400,0x30153360,0xb2e1ae31,0xb385b3ab,0x2d76ac93,0xb166a691,0xb1e7b3f5,
  0x22deb06a,0x33fd32ac,0xb337b3da,0x2ee8aa19,0x2f853387,0xb310ad6a,0x322d33fe,0xb1162216,0xb2a9abd3,0xb06fb3c2,0xb07428a6,0xb2a5b3ea,
  0xb111b3e9,0x323128be,0xb30db3c3,0x2f90abba,0x31aa227a,0x31a633fd,0x2e25ad5e,0x33633389,0x2d6a3365,0xb387ae1a,0xa21631aa,0xb3feb1a6,
  0xb3c2af85,0xabd3b310,0xb3eab22d,0x28a6b116,0xa8beb2a9,0x33e9306f,0x2bbab074,0x33c332a5,0x33fd3111,0x227a3231,0x3389330d,0xad5e2f90,
  0x2a63333f,0xb3d7aec6,0xb2a2a1b1,0xb07ab3fe,0xb3f7b158,0x25fbb1f4,0xacb7b38b,0x33a52d52,0x2e0eb025,0x336832d8,0x340030bc,0x14b63273,
  0x323533c0,0xb10c2beb,0xac9330cc,0xb3abb267,0x23433316,0xb3fdaf6f,0xb38eb225,0x2d46b11f,0xb342b29e,0x2ebbb07f,0x31e3aa7c,0x316b33d6,
  0x3264a6c3,0x30d133f5,0x2c0233ac,0xb3bfac87,0x28f0336a,0xb3e7ae02,0xb3c6b19d,0x2b89b1b3,0xa59732e8,0xb3f8b00a,0xaccfb3ed,0x33a1285b,
  0xb1b8b381,0x3199ad8d,0x336c31df,0xadf73170,0x33f42d3a,0x26f53390,0xb30423a7,0xafb2b3fc,0xb05f3030,0xb2b3b2d1,0x29e8b27a,0x33dd30b2,
  0xab5932b6,0xb3c9b05a,0x30adb089,0x327e3297,0xaf0ab3f3,0x332fa727,0x240633b0,0xb3fcac6f,0x33473194,0xaea431bc,0xb174b359,0x31daae54,
  0xb3bca565,0xac1ab3f9,0x33ee2f59,0xa842331b,0xaddf3281,0xb371b0a8,0x34002b40,0x1c5233cb,0xa759b3ef,0x33f22829,0xb2fe2c26,0xafc8b3ba,
  0x308e337c,0xb2932da5,0x3055b179,0x32ba31d6,0xb31eb146,0x2f4eb204,0xa5333394,0xb3f9ad23,0xaff33249,0xb2f1b0f3,0x30e532fb,0xb2542fd2,
  0x2b28b373,0x33cc2dd4,0xb285b18b,0x30a3b1c5,0x246a33fa,0xb3fba500,0x33962f42,0xad173321,0xadb1b3d0,0x337aaade,0xb3ffa99e,0x1f76b3e0,
  0xb0ee320d,0xb24db13c,0xac4b3398,0xb3b5ad0b,0x304ab289,0x32c1309e,0x2985b3ce,0x33e12b0f,0xaf3732f4,0xb324afe8,0xa4ce33f0,0xb3faa7ef,
  0x2dc8b34f,0x33762e82,0x9de4b3ff,0x33ff1ead,0xb1c931cd,0xb186b182,0xb3762e82,0xadc8b34f,0x324db13c,0x30ee320d,0x33b5ad0b,0x2c4b3398,
  0xb2c1309e,0xb04ab289,0xb3e12b0f,0xa985b3ce,0x3324afe8,0x2f3732f4,0x33faa7ef,0x24ce33f0,0xb285318b,0xb0a3b1c5,0xb2c7ae6b,0x3040b354,
  0x3396af42,0x2d173321,0x31413133,0xb2093215,0xb3ff299e,0x9f76b3e0,0xae8db2bd,0x334cb050,0x33b8278b,0xac3233f2,0x281033b3,0xb3ef2c57,
  0xb31e3146,0xaf4eb204,0xa533b394,0x33f9ad23,0x3400ab40,0x9c5233cb,0xae5f33e4,0xb357a93b,0xb2feac26,0x2fc8b3ba,0x3245b258,0x30f830e0,
  0x30553179,0xb2ba31d6,0xb3df2e99,0xa9b6b34a,0xb39230fd,0xad2fb241,0x3200b301,0x314a2fbd,0x337f1b11,0xad993400,0xb3ff2deb,0xa084b36f,
  0xb005b129,0x32ebb21d,0x325c2cdb,0xb0db339f,0xa92233de,0xb3e529cf,0xab59b2b6,0x33c9b05a,0xb3dd30b2,0xa9e8b27a,0x33d4ab71,0xaa9433c8,
  0x32212c0e,0xb12433bd,0xaf64b0d6,0x3318b260,0x197fb345,0x3400aeaf,0xae4833fe,0xb35c20e8,0xb23d3332,0xb102aeff,0x33aeb14f,0x2c7b31fc,
  0xb3fe3065,0xa14db2b0,0x2ebb307f,0xb342329e,0x300f2fa6,0xb2e53307,0x30d1b3f5,0x326426c3,0x302ab400,0x32d517db,0xb3e72e02,0x28f0b36a,
  0xb3fd2f6f,0x2343b316,0x2d46311f,0xb38e3225,0xb3f53015,0x2691b2e1,0xaf9b33eb,0xb30a288d,0x2a193166,0xb3da31e7,0x33d7aec6,0xaa63333f,
  0x3313b337,0x2f7a2ee8,0xa5fbb1f4,0x33f7b158,0xb1a1a8d7,0x31afb3e8,0xb36832d8,0xae0eb025,0xb3c22f85,0x2bd3b310,0xb3ea322d,0xa8a6b116,
  0xa8be32a9,0xb3e9306f,0x2bba3074,0xb3c332a5,0x33fdb111,0xa27a3231,0x3389b30d,0x2d5e2f90,0xa216b1aa,0x33feb1a6,0xaed2ae25,0x333db363,
  0xb3652edd,0x2e1ab33a,0xb1aa227a,0x31a6b3fd,0xaf853387,0xb3102d6a,0xb22d33fe,0xb116a216,0x32a9abd3,0xb06f33c2,0x307428a6,0xb2a533ea,
  0x3111b3e9,0x3231a8be,0x330db3c3,0x2f902bba,0xb2e12e31,0x3015b360,0x288db1a1,0x33ebb1af,0xb1e733f5,0xb1662691,0xb33f2f9b,0x2ec6b30a,
  0x2ee82a19,0xb33733da,0xb15833d7,0xb1f42a63,0x33e8b313,0x28d72f7a,0x302525fb,0xb2d833f7,0xb2392d81,0x3107b383,0x3307b3fe,0x2fa6214d,
  0xb35e33ec,0xae3ca874,0x97dbb00f,0x3400b2e5,0xa5c930b7,0xb3f83276,0xb316302a,0x2f6fb2d5,0x32b0aef4,0xb0653335,0xb29e33fd,0xb07f2343,
  0xb1702ccf,0x31dfb3a1,0x3345b124,0xaeaf3221,0xb3fc336c,0xa3a7adf7,0x3332b400,0x2eff997f,0xb0b23304,0xb27a2fb2,0x2b71b102,0x33c8b23d,
  0x2c0e29e8,0xb3bd33dd,0xb0d62a94,0x3260b3d4,0xb0892c1a,0x3297b3bc,0x2aad2842,0xb3d333ee,0xb3b0327e,0x2c6fb0ad,0x3241b035,0xb0fd32ce,
  0xb35933fc,0xae542406,0x3400b392,0x1b112d2f,0xaf5931da,0xb31b3174,0x321db37f,0x3129ad99,0xaf152ac6,0x332cb3d2,0xb1463293,0xb204308e,
  0xb281312e,0x30a8b219,0xab402f4e,0xb3cb331e,0xb3ef3371,0x2829addf,0x2c269c52,0xb3ba3400,0xb37c33f2,0xada52759,0x3179afc8,0xb1d632fe,
  0xacf32953,0x339cb3e3,0xb3fa33cc,0x2500ab28,0xb0942f21,0x3290b32a,0xb3d033fb,0xaade246a,0xb249317d,0x30f3b1d2,0xb2fb337a,0xafd22db1,
  0xb37332f1,0x2dd4aff3,0xb18b3254,0xb1c530e5,0xa96c27bd,0x33e2b3f1,0xb0452fdd,0x32c4b2f7,0xac3e2af7,0x33b7b3cf,0xb0ea3099,0x3250b28c,
  0xadbc2cff,0x3378b39a,0xb1823137,0x31cdb211,0xaf2c2e76,0x3327b352,0xb20d31c9,0x313cb186,0x313c3186,0xb20db1c9,0x2d0b2dc8,0xb398b376,
  0x309e30ee,0xb289b24d,0x2b0f2c4b,0xb3ceb3b5,0x2fe8304a,0xb2f4b2c1,0x27ef2985,0xb3f0b3e1,0x2e822f37,0xb34fb324,0x1ead24ce,0xb3ffb3fa,
  0xb2bdb209,0xb050b141,0xb290b32a,0x30942f21,0xb3b3b34c,0xac57ae8d,0xb0f3b1d2,0x3249317d,0xb400b3ef,0x1d1ba810,0xadd4aff3,0x337332f1,
  0xb39cb3e3,0x2cf32953,0xa500ab28,0x33fa33cc,0xae99b0f8,0x334a3245,0x33ff33b2,0x201f2c63,0x2438a9b6,0x33fc33df,0x332c33d2,0xaf15aac6,
  0x303a2ce7,0x32cb339e,0x30a83219,0xb281b12e,0x32ee31c0,0x2ffe3190,0x28292ddf,0xb3efb371,0x33b0327e,0x2c6f30ad,0xb241b035,0xb0fdb2ce,
  0x335933fc,0xae54a406,0xb400b392,0x1b11ad2f,0x2f5931da,0xb31bb174,0xb21db37f,0x31292d99,0xaaad2842,0xb3d3b3ee,0xa9cfb005,0x33de32eb,
  0x285b305f,0xb3edb2b3,0x2c0ea9e8,0x33bd33dd,0xb170accf,0xb1dfb3a1,0x33453124,0x2eaf3221,0xb3fcb36c,0x23a7adf7,0x33323400,0xaeff997f,
  0xb0b2b304,0x327a2fb2,0x2b713102,0xb3c8b23d,0xb400b2e5,0x17dbb00f,0x2e023264,0xb36ab0d1,0xaf6fb2d5,0x3316302a,0xb11fa8f0,0xb225b3e7,
  0x307f2343,0x329e33fd,0xb3d6b38e,0x2a7cad46,0x33f53342,0xa6c32ebb,0xac87b1e3,0x33ac316b,0x28d7af7a,0x33e83313,0xb2d8b3f7,0x3025a5fb,
  0x33eb31af,0x288d31a1,0x2bebae0e,0x33c03368,0x2ec6330a,0xb33faf9b,0x33fe3235,0x21b1310c,0xb1f4aa63,0xb158b3d7,0x2d5232a2,0xb38bb07a,
  0x33a7333d,0xacab2ed2,0x33f63162,0x262d31eb,0xaa4b301a,0xb3d8b2de,0x2a32326b,0xb3d9b0c7,0xb3f6b26f,0x265fb0c1,0xb3a9b020,0xac9fb2db,
  0x0e48b15d,0x340031f0,0xae1ab33a,0x33652edd,0xaed22e25,0xb33db363,0xb1eb0e48,0xb162b400,0xb2deb3a7,0x301aacab,0xb0c7b3f6,0x326b262d,
  0x30c1aa4b,0x326f33d8,0x32db2a32,0x302033d9,0x31f033f6,0xb15d265f,0x2edd33a9,0xb33aac9f,0xb2acb385,0x306aad76,0x2a19b166,0x33da31e7,
  0x3229a2de,0x311b33fd,0x33133337,0xaf7a2ee8,0x2e3133c5,0xb360aba2,0xb1a128d7,0xb1afb3e8,0xb3f5b015,0xa691b2e1,0xaf9bb3eb,0x330a288d,
  0x3154acc3,0x31f833a3,0x2ef433f8,0xb335a5c9,0x2d8133dc,0xb383aa01,0xb3feb065,0x214db2b0,0xb3ecb107,0x2874b239,0x300fafa6,0x32e53307,
  0x30b7ae3c,0x3276335e,0x302a3400,0xb2d517db,0x312433bd,0xb2212c0e,0xb318b260,0x2f64b0d6,0xb400aeaf,0x997fb345,0x335c20e8,0x2e4833fe,
  0x3102aeff,0x323d3332,0xac7b31fc,0xb3aeb14f,0x2a9433c8,0xb3d4ab71,0xb084b3e6,0x329ba909,0xb2ce2aad,0xb035b3d3,0x33e529cf,0x292233de,
  0x2d2fb241,0x339230fd,0xb14a2fbd,0xb200b301,0x2d993400,0xb37f1b11,0x2084b36f,0x33ff2deb,0xb2ebb21d,0x3005b129,0x30db339f,0xb25c2cdb,
  0xae5fb3e4,0x3357a93b,0xb190303a,0xb1c0b2cb,0x32453258,0xb0f830e0,0x2c63b2ee,0x33b22ffe,0xb3dfae99,0x29b6b34a,0x2ac633ff,0xb3d2a01f,
  0x339ea438,0x2ce733fc,0xb12eb32c,0x3219af15,0x33b8a78b,0x2c3233f2,0x2810b3b3,0x33ef2c57,0xb2c72e6b,0xb040b354,0x29533400,0xb3e31d1b,
  0x3141b133,0x32093215,0xaf21b39c,0x332aacf3,0xae8d32bd,0xb34cb050,0x317d3290,0xb1d23094,0x27bd33fb,0xb3f1249c,0x2fdd3327,0xb2f72f2c,
  0xaaf7b3e2,0x33cfa96c,0xb099b2c4,0x328cb045,0x2cff33b7,0xb39a2c3e,0x31373250,0xb21130ea,0xae76b378,0x3352adbc,0xb1c9b1cd,0x3186b182,
  0xb3ff1ead,0x1de4b3ff,0xb352adbc,0x2e76b378,0x33f1249c,0xa7bd33fb,0x32f72f2c,0xafdd3327,0xb3cfa96c,0x2af7b3e2,0xb28cb045,0x3099b2c4,
  0x339a2c3e,0xacff33b7,0x321130ea,0xb1373250,0x2953b400,0x33e31d1b,0x33ccadd4,0x2b283373,0xaf21339c,0xb32aacf3,0xb3fb2500,0x246ab3fa,
  0x317db290,0x31d23094,0x337a2ade,0xadb133d0,0xb2f130f3,0xaff3b249,0xb254afd2,0x30e5b2fb,0x339e2438,0xace733fc,0xb12e332c,0xb219af15,
  0xb190b03a,0x31c0b2cb,0x3371b0a8,0x2ddf3281,0x2c6332ee,0xb3b22ffe,0xb3f22829,0x2759b3ef,0x2ac6b3ff,0x33d2a01f,0x32932da5,0xb08e337c,
  0xaf0a33f3,0xb32fa727,0x2406b3b0,0x33fcac6f,0x3347b194,0x2ea431bc,0xb1743359,0xb1daae54,0xb3bc2565,0x2c1ab3f9,0x33eeaf59,0x2842331b,
  0x30ad3089,0xb27e3297,0xb2ceaaad,0x3035b3d3,0xb29ba909,0x3084b3e6,0x305f3030,0xb2b332d1,0x259732e8,0xb3f8300a,0x2ccfb3ed,0x33a1a85b,
  0x31b8b381,0x31992d8d,0xb36c31df,0xadf7b170,0xb3f42d3a,0x26f5b390,0x330423a7,0xafb233fc,0x316bb3d6,0x31e32a7c,0xb3832a01,0x2d81b3dc,
  0xb3bf2c87,0x2c02b3ac,0x28743239,0xb3ec3107,0x2b8931b3,0xb3c6319d,0x3276b35e,0x30b72e3c,0x31f8b3a3,0x31542cc3,0xb33525c9,0x2ef4b3f8,
  0x310c2beb,0xb23533c0,0x33abb267,0x2c9330cc,0x307ab3fe,0x32a2a1b1,0xb06aad76,0x32acb385,0xb3a52d52,0x2cb7b38b,0xb11b33fd,0xb229a2de,
  0x94b63273,0xb40030bc,0x3360aba2,0xae3133c5,0xb2de33a7,0xb01aacab,0xb0c733f6,0xb26b262d,0x30c12a4b,0xb26f33d8,0x32dbaa32,0xb02033d9,
  0x31f0b3f6,0x315d265f,0x2eddb3a9,0x333aac9f,0xb1eb8e48,0x3162b400,0xb3872e1a,0x2d6ab365,0xae25ad5e,0x3363b389,0x8e48b15d,0x3400b1f0,
  0xb3a7333d,0xacabaed2,0xb3f63162,0x262db1eb,0x2a4b301a,0xb3d832de,0xaa32326b,0xb3d930c7,0x33f6b26f,0x265f30c1,0x33a9b020,0xac9f32db,
  0x33c0b368,0x2beb2e0e,0x30cc94b6,0xb2673400,0x21b1b10c,0x33feb235,0x3385b3ab,0x2d762c93,0xb38b307a,0x2d52b2a2,0xa2deb06a,0x33fdb2ac,
  0xb0bc33a5,0xb2732cb7,0xb3c5311b,0x2ba2b229,0x26c32ebb,0xb3f53342,0xb3ac316b,0x2c87b1e3,0x336ab0d1,0xae023264,0xb19d33bf,0xb1b32c02,
  0x3225b3e7,0x311fa8f0,0x2cc32b89,0xb3a333c6,0xaa7cad46,0x33d6b38e,0x33dcb1f8,0xaa013154,0xb3fe3318,0x20e8af64,0x3381b3f8,0x2d8d2597,
  0xb14f335c,0xb1fc2e48,0x2d3ab199,0x3390b1b8,0x29092c7b,0xb3e633ae,0xb03026f5,0x32d1b3f4,0x32e8b084,0xb00a329b,0xb3ed32b3,0x285bb05f,
  0x29cfb005,0x33deb2eb,0xb05a325c,0xb2b630db,0xafbd2922,0x3301b3e5,0x27272b59,0xb3f333c9,0xb36f3200,0x2debb14a,0x31bcaf0a,0xb194332f,
  0xb39f33ff,0xacdba084,0x33f9b347,0xa5652ea4,0x3394b2ba,0xad233055,0xa438a9b6,0x33fcb3df,0x33e4b3f9,0x293b2533,0xb03a2ce7,0x32cbb39e,
  0x3258b357,0x30e0ae5f,0xb2ee31c0,0x2ffeb190,0x2e99b0f8,0x334ab245,0xb3ff33b2,0x201fac63,0xaf4230a3,0xb3213285,0x3133b040,0xb21532c7,
  0xa99e2d17,0xb3e03396,0x32bdb209,0xb0503141,0x278b1f76,0xb3f233ff,0x33b3b34c,0xac572e8d,0x2e6bac32,0xb35433b8,0x3400b3ef,0x1d1b2810,
  0xb289324d,0x309eb0ee,0xb3ce33b5,0x2b0fac4b,0xb2f432c1,0x2fe8b04a,0xb3f033e1,0x27efa985,0xb34f3324,0x2e82af37,0xb3ff33fa,0x1eada4ce,
  0xb3983376,0x2d0badc8,0xb3fb33ff,0xa49c1de4,0x351c35f6,0xac93a617,0xb8a3b93c,0x308d2a16,0x32f43448,0xb160afa5,0xb6a4b7fe,0x353a3389,
  0x2fa53160,0xb448b2f4,0xb389b53a,0x37fe36a4,0x26172c93,0xb5f6b51c,0xaa16b08d,0x393c38a3,0x34c3358c,0xac47a5b2,0xb85fb8f3,0x304229b1,
  0x327e33fd,0xb106af26,0xb63cb785,0x34e7330f,0x2f263106,0xb3fdb27e,0xb30fb4e7,0x3785363c,0x25b22c47,0xb58cb4c3,0xa9b1b042,0x38f3385f,
  0x346a3523,0xabf6a54d,0xb81ab8a8,0x2fef294d,0x3209336b,0xb0acaea7,0xb5d4b70a,0x34933294,0x2ea730ac,0xb36bb209,0xb294b493,0x370a35d4,
  0x254d2bf6,0xb523b46a,0xa94dafef,0x38a8381a,0x341334bc,0xab5fa4e9,0xb7a6b85a,0x2f5928e8,0x319432da,0xb052ae28,0xb56ab68d,0x343e3219,
  0x2e283052,0xb2dab194,0xb219b43e,0x368d356a,0x24e92b5f,0xb4bcb413,0xa8e8af59,0x385a37a6,0x33783456,0xaac8a484,0xb715b80a,0x2ec32884,
  0x3120324a,0xaff2ada9,0xb4ffb60e,0x33d3319e,0x2da92ff2,0xb24ab120,0xb19eb3d3,0x360e34ff,0x24842ac8,0xb456b378,0xa884aec3,0x380a3715,
  0x32cd33e3,0xaa31a420,0xb682b76f,0x2e2d281f,0x30ac31bb,0xaf3fad2a,0xb493b58d,0x33283122,0x2d2a2f3f,0xb1bbb0ac,0xb122b328,0x358d3493,
  0x24202a31,0xb3e3b2cd,0xa81fae2d,0x376f3682,0x3223331c,0xa999a376,0xb5ebb6c6,0x2d972776,0x3039312d,0xae8dacac,0xb426b50b,0x327c30a6,
  0x2cac2e8d,0xb12db039,0xb0a6b27c,0x350b3426,0x23762999,0xb31cb223,0xa776ad97,0x36c635eb,0x317a3257,0xa902a2ad,0xb552b61a,0x2d0026ad,
  0x2f8c309f,0xaddcac2e,0xb371b487,0x31cf3029,0x2c2e2ddc,0xb09faf8c,0xb029b1cf,0x34873371,0x22ad2902,0xb257b17a,0xa6adad00,0x361a3552,
  0x30d23194,0xa86ba1e4,0xb4b7b56a,0x2c6a25e4,0x2ea73012,0xad2aab5f,0xb294b402,0x31222f59,0x2b5f2d2a,0xb012aea7,0xaf59b122,0x34023294,
  0x21e4286b,0xb194b0d2,0xa5e4ac6a,0x356a34b7,0x302c30d2,0xa7a9a11b,0xb41ab4b7,0x2ba7251b,0x2dc22f0c,0xac79aa63,0xb1b6b2f7,0x30742e5f,
  0x2a632c79,0xaf0cadc2,0xae5fb074,0x32f731b6,0x211b27a9,0xb0d2b02c,0xa51baba7,0x34b7341a,0x2f0c3012,0xa67ba052,0xb2f7b402,0x2a7a2452,
  0x2cde2df5,0xab91a967,0xb0d7b1e8,0x2f8b2d65,0x29672b91,0xadf5acde,0xad65af8b,0x31e830d7,0x2052267b,0xb012af0c,0xa452aa7a,0x340232f7,
  0x2dc22ea7,0xa54d9f12,0xb1b6b294,0x294d2311,0x2bf62cde,0xaa31a86b,0xafefb0d7,0x2e2d2c6a,0x286b2a31,0xacdeabf6,0xac6aae2d,0x30d72fef,
  0x1f12254d,0xaea7adc2,0xa311a94d,0x329431b6,0x2c792d2a,0xa4209d7f,0xb074b122,0x281f217f,0x2a312b91,0xa8d0a6e0,0xae2daf8b,0x2cce2ade,
  0x26e028d0,0xab91aa31,0xaadeacce,0x2f8b2e2d,0x1d7f2420,0xad2aac79,0xa17fa81f,0x31223074,0x2a632b5f,0xa1e49bdb,0xae5faf59,0x25e41fdb,
  0x286b2967,0xa6e0a4e9,0xac6aad65,0x2ade28e8,0x24e926e0,0xa967a86b,0xa8e8aade,0x2d652c6a,0x1bdb21e4,0xab5faa63,0x9fdba5e4,0x2f592e5f,
  0x27a9286b,0x9f1298b6,0xaba7ac6a,0x23111cb6,0x254d267b,0xa420a1e4,0xa94daa7a,0x281f25e4,0x21e42420,0xa67ba54d,0xa5e4a81f,0x2a7a294d,
  0x18b61f12,0xa86ba7a9,0x9cb6a311,0x2c6a2ba7,0x211b21e4,0x98b69248,0xa51ba5e4,0x1cb61648,0x1f122052,0x9d7f9bdb,0xa311a452,0x217f1fdb,
  0x1bdb1d7f,0xa0529f12,0x9fdba17f,0x24522311,0x124818b6,0xa1e4a11b,0x96489cb6,0x25e4251b,0xa11ba1e4,0x18b61248,0x251b25e4,0x9cb69648,
  0x9f12a052,0x1d7f1bdb,0x23112452,0xa17f9fdb,0x9bdb9d7f,0x20521f12,0x1fdb217f,0xa452a311,0x924898b6,0x21e4211b,0x16481cb6,0xa5e4a51b,
  0xa7a9a86b,0x1f1218b6,0x2ba72c6a,0xa3119cb6,0xa54da67b,0x242021e4,0x294d2a7a,0xa81fa5e4,0xa1e4a420,0x267b254d,0x25e4281f,0xaa7aa94d,
  0x98b69f12,0x286b27a9,0x1cb62311,0xac6aaba7,0xaa63ab5f,0x21e41bdb,0x2e5f2f59,0xa5e49fdb,0xa86ba967,0x26e024e9,0x2c6a2d65,0xaadea8e8,
  0xa4e9a6e0,0x2967286b,0x28e82ade,0xad65ac6a,0x9bdba1e4,0x2b5f2a63,0x1fdb25e4,0xaf59ae5f,0xac79ad2a,0x24201d7f,0x30743122,0xa81fa17f,
  0xaa31ab91,0x28d026e0,0x2e2d2f8b,0xacceaade,0xa6e0a8d0,0x2b912a31,0x2ade2cce,0xaf8bae2d,0x9d7fa420,0x2d2a2c79,0x217f281f,0xb122b074,
  0xadc2aea7,0x254d1f12,0x31b63294,0xa94da311,0xabf6acde,0x2a31286b,0x2fef30d7,0xae2dac6a,0xa86baa31,0x2cde2bf6,0x2c6a2e2d,0xb0d7afef,
  0x9f12a54d,0x2ea72dc2,0x2311294d,0xb294b1b6,0xaf0cb012,0x267b2052,0x32f73402,0xaa7aa452,0xacdeadf5,0x2b912967,0x30d731e8,0xaf8bad65,
  0xa967ab91,0x2df52cde,0x2d652f8b,0xb1e8b0d7,0xa052a67b,0x30122f0c,0x24522a7a,0xb402b2f7,0xb02cb0d2,0x27a9211b,0x341a34b7,0xaba7a51b,
  0xadc2af0c,0x2c792a63,0x31b632f7,0xb074ae5f,0xaa63ac79,0x2f0c2dc2,0x2e5f3074,0xb2f7b1b6,0xa11ba7a9,0x30d2302c,0x251b2ba7,0xb4b7b41a,
  0xb0d2b194,0x286b21e4,0x34b7356a,0xac6aa5e4,0xaea7b012,0x2d2a2b5f,0x32943402,0xb122af59,0xab5fad2a,0x30122ea7,0x2f593122,0xb402b294,
  0xa1e4a86b,0x319430d2,0x25e42c6a,0xb56ab4b7,0xb17ab257,0x290222ad,0x3552361a,0xad00a6ad,0xaf8cb09f,0x2ddc2c2e,0x33713487,0xb1cfb029,
  0xac2eaddc,0x309f2f8c,0x302931cf,0xb487b371,0xa2ada902,0x3257317a,0x26ad2d00,0xb61ab552,0xb223b31c,0x29992376,0x35eb36c6,0xad97a776,
  0xb039b12d,0x2e8d2cac,0x3426350b,0xb27cb0a6,0xacacae8d,0x312d3039,0x30a6327c,0xb50bb426,0xa376a999,0x331c3223,0x27762d97,0xb6c6b5eb,
  0xb2cdb3e3,0x2a312420,0x3682376f,0xae2da81f,0xb0acb1bb,0x2f3f2d2a,0x3493358d,0xb328b122,0xad2aaf3f,0x31bb30ac,0x31223328,0xb58db493,
  0xa420aa31,0x33e332cd,0x281f2e2d,0xb76fb682,0xb378b456,0x2ac82484,0x3715380a,0xaec3a884,0xb120b24a,0x2ff22da9,0x34ff360e,0xb3d3b19e,
  0xada9aff2,0x324a3120,0x319e33d3,0xb60eb4ff,0xa484aac8,0x34563378,0x28842ec3,0xb80ab715,0xb413b4bc,0x2b5f24e9,0x37a6385a,0xaf59a8e8,
  0xb194b2da,0x30522e28,0x356a368d,0xb43eb219,0xae28b052,0x32da3194,0x3219343e,0xb68db56a,0xa4e9ab5f,0x34bc3413,0x28e82f59,0xb85ab7a6,
  0xb46ab523,0x2bf6254d,0x381a38a8,0xafefa94d,0xb209b36b,0x30ac2ea7,0x35d4370a,0xb493b294,0xaea7b0ac,0x336b3209,0x32943493,0xb70ab5d4,
  0xa54dabf6,0x3523346a,0x294d2fef,0xb8a8b81a,0xb4c3b58c,0x2c4725b2,0x385f38f3,0xb042a9b1,0xb27eb3fd,0x31062f26,0x363c3785,0xb4e7b30f,
  0xaf26b106,0x33fd327e,0x330f34e7,0xb785b63c,0xa5b2ac47,0x358c34c3,0x29b13042,0xb8f3b85f,0xb51cb5f6,0x2c932617,0x38a3393c,0xb08daa16,
  0xb2f4b448,0x31602fa5,0x36a437fe,0xb53ab389,0xafa5b160,0x344832f4,0x3389353a,0xb7feb6a4,0xa617ac93,0x35f6351c,0x2a16308d,0xb93cb8a3,
};
__device__ __align__(128) const uint32_t c_img[2560] = {
  0x326d31ed,0x333b32dd,0x33c33388,0x33fe33ea,0x33c331ed,0x31ed33c3,0xa8b22d64,0xb33bb0c4,0x33ea31ed,0xad64301d,0xb2ddb388,0x315fa8b2,
  0x32dd31ed,0xb3feabc6,0x326dad64,0xad64326d,0x30c431ed,0xaed7b2dd,0x2bc63388,0xa248b3ea,0x2bc631ed,0x315fb3c3,0xb3ea2d64,0x2ed730c4,
  0xa8b231ed,0x3388b01d,0x301db388,0xb1ed28b2,0xb01d31ed,0x22482bc6,0x30c4ad64,0x3388b26d,0x33ea33fe,0x338833c3,0x32dd333b,0x31ed326d,
  0xb2ddb3fe,0xa248b01d,0x326d2ed7,0x338833ea,0x30c433fe,0xb33babc6,0xabc6b33b,0x33fe30c4,0xabc6b3fe,0x31ed32dd,0xb3eaaed7,0x333ba8b2,
  0xa8b233fe,0x2d64b3c3,0xb01d333b,0x315fb26d,0x301db3fe,0xb3fe301d,0x30c42ed7,0x2d64b3ea,0xb26d33fe,0x2ed72bc6,0x33c3b33b,0xa248b0c4,
  0x33c3b3fe,0x315fb2dd,0x28b2aed7,0xaed728b2,0xb0c4b15f,0xaed7b01d,0xabc6ad64,0xa248a8b2,0xabc6b15f,0x315f2bc6,0x33ea3388,0x2ed7326d,
  0x28b2b15f,0x338832dd,0xb01d2d64,0xb1edb3ea,0x301db15f,0x224833c3,0xb0c4b388,0x338830c4,0x326db15f,0xb33b301d,0x33c3ad64,0xb3fe28b2,
  0x33c3b15f,0xb1edabc6,0xa8b23388,0x333bb26d,0x33eab15f,0x2d64b2dd,0xb2dd2d64,0xb15f33ea,0x32ddb15f,0x33feb3c3,0x326db388,0x2d64b0c4,
  0x28b22248,0x2d642bc6,0x301d2ed7,0x315f30c4,0xb01da248,0xb3feb2dd,0xb0c4b33b,0x2d64a8b2,0x326d2248,0x2ed733c3,0xb3c3aed7,0xa248b26d,
  0xb3c3a248,0x315fb01d,0xa8b2333b,0xaed7b3ea,0x33ea2248,0xb388abc6,0x32dd2ed7,0xb1edb0c4,0xb2dda248,0x224832dd,0x326db33b,0xb38828b2,
  0x30c42248,0x333bb3c3,0xabc6aed7,0xb3fe326d,0xabc6a248,0xb1ed301d,0xb3ea333b,0xb33b33ea,0xb26d31ed,0xb33b32dd,0xb3c33388,0xb3fe33ea,
  0xb3c331ed,0xb1ed33c3,0x28b22d64,0x333bb0c4,0xb3ea31ed,0x2d64301d,0x32ddb388,0xb15fa8b2,0xb2dd31ed,0x33feabc6,0xb26dad64,0x2d64326d,
  0xb0c431ed,0x2ed7b2dd,0xabc63388,0x2248b3ea,0xabc631ed,0xb15fb3c3,0x33ea2d64,0xaed730c4,0x28b231ed,0xb388b01d,0xb01db388,0x31ed28b2,
  0x301d31ed,0xa2482bc6,0xb0c4ad64,0xb388b26d,0xb3ea33fe,0xb38833c3,0xb2dd333b,0xb1ed326d,0x32ddb3fe,0x2248b01d,0xb26d2ed7,0xb38833ea,
  0xb0c433fe,0x333babc6,0x2bc6b33b,0xb3fe30c4,0x2bc6b3fe,0xb1ed32dd,0x33eaaed7,0xb33ba8b2,0x28b233fe,0xad64b3c3,0x301d333b,0xb15fb26d,
  0xb01db3fe,0x33fe301d,0xb0c42ed7,0xad64b3ea,0x326d33fe,0xaed72bc6,0xb3c3b33b,0x2248b0c4,0xb3c3b3fe,0xb15fb2dd,0xa8b2aed7,0x2ed728b2,
  0x30c4b15f,0x2ed7b01d,0x2bc6ad64,0x2248a8b2,0x2bc6b15f,0xb15f2bc6,0xb3ea3388,0xaed7326d,0xa8b2b15f,0xb38832dd,0x301d2d64,0x31edb3ea,
  0xb01db15f,0xa24833c3,0x30c4b388,0xb38830c4,0xb26db15f,0x333b301d,0xb3c3ad64,0x33fe28b2,0xb3c3b15f,0x31edabc6,0x28b23388,0xb33bb26d,
  0xb3eab15f,0xad64b2dd,0x32dd2d64,0x315f33ea,0xb2ddb15f,0xb3feb3c3,0xb26db388,0xad64b0c4,0xa8b22248,0xad642bc6,0xb01d2ed7,0xb15f30c4,
  0x301da248,0x33feb2dd,0x30c4b33b,0xad64a8b2,0xb26d2248,0xaed733c3,0x33c3aed7,0x2248b26d,0x33c3a248,0xb15fb01d,0x28b2333b,0x2ed7b3ea,
  0xb3ea2248,0x3388abc6,0xb2dd2ed7,0x31edb0c4,0x32dda248,0xa24832dd,0xb26db33b,0x338828b2,0xb0c42248,0xb33bb3c3,0x2bc6aed7,0x33fe326d,
  0x2bc6a248,0x31ed301d,0x33ea333b,0x333b33ea,0x30c4315f,0x2ed7301d,0x2bc62d64,0x224828b2,0x2bc6315f,0xb15fabc6,0xb3eab388,0xaed7b26d,
  0xa8b2315f,0xb388b2dd,0x301dad64,0x31ed33ea,0xb01d315f,0xa248b3c3,0x30c43388,0xb388b0c4,0xb26d315f,0x333bb01d,0xb3c32d64,0x33fea8b2,
  0xb3c3315f,0x31ed2bc6,0x28b2b388,0xb33b326d,0xb3ea315f,0xad6432dd,0x32ddad64,0x315fb3ea,0xb2dd315f,0xb3fe33c3,0xb26d3388,0xad6430c4,
  0xa8b2a248,0xad64abc6,0xb01daed7,0xb15fb0c4,0x301d2248,0x33fe32dd,0x30c4333b,0xad6428b2,0xb26da248,0xaed7b3c3,0x33c32ed7,0x2248326d,
  0x33c32248,0xb15f301d,0x28b2b33b,0x2ed733ea,0xb3eaa248,0x33882bc6,0xb2ddaed7,0x31ed30c4,0x32dd2248,0xa248b2dd,0xb26d333b,0x3388a8b2,
  0xb0c4a248,0xb33b33c3,0x2bc62ed7,0x33feb26d,0x2bc62248,0x31edb01d,0x33eab33b,0x333bb3ea,0x326d31ed,0x333b32dd,0x33c33388,0x33fe33ea,
  0x33c331ed,0x31ed33c3,0xa8b22d64,0xb33bb0c4,0x33ea31ed,0xad64301d,0xb2ddb388,0x315fa8b2,0x32dd31ed,0xb3feabc6,0x326dad64,0xad64326d,
  0x30c431ed,0xaed7b2dd,0x2bc63388,0xa248b3ea,0x2bc631ed,0x315fb3c3,0xb3ea2d64,0x2ed730c4,0xa8b231ed,0x3388b01d,0x301db388,0xb1ed28b2,
  0xb01d31ed,0x22482bc6,0x30c4ad64,0x3388b26d,0x33ea33fe,0x338833c3,0x32dd333b,0x31ed326d,0xb2ddb3fe,0xa248b01d,0x326d2ed7,0x338833ea,
  0x30c433fe,0xb33babc6,0xabc6b33b,0x33fe30c4,0xabc6b3fe,0x31ed32dd,0xb3eaaed7,0x333ba8b2,0xa8b233fe,0x2d64b3c3,0xb01d333b,0x315fb26d,
  0x301db3fe,0xb3fe301d,0x30c42ed7,0x2d64b3ea,0xb26d33fe,0x2ed72bc6,0x33c3b33b,0xa248b0c4,0x33c3b3fe,0x315fb2dd,0x28b2aed7,0xaed728b2,
  0xb0c4315f,0xaed7301d,0xabc62d64,0xa24828b2,0xabc6315f,0x315fabc6,0x33eab388,0x2ed7b26d,0x28b2315f,0x3388b2dd,0xb01dad64,0xb1ed33ea,
  0x301d315f,0x2248b3c3,0xb0c43388,0x3388b0c4,0x326d315f,0xb33bb01d,0x33c32d64,0xb3fea8b2,0x33c3315f,0xb1ed2bc6,0xa8b2b388,0x333b326d,
  0x33ea315f,0x2d6432dd,0xb2ddad64,0xb15fb3ea,0x32dd315f,0x33fe33c3,0x326d3388,0x2d6430c4,0x28b2a248,0x2d64abc6,0x301daed7,0x315fb0c4,
  0xb01d2248,0xb3fe32dd,0xb0c4333b,0x2d6428b2,0x326da248,0x2ed7b3c3,0xb3c32ed7,0xa248326d,0xb3c32248,0x315f301d,0xa8b2b33b,0xaed733ea,
  0x33eaa248,0xb3882bc6,0x32ddaed7,0xb1ed30c4,0xb2dd2248,0x2248b2dd,0x326d333b,0xb388a8b2,0x30c4a248,0x333b33c3,0xabc62ed7,0xb3feb26d,
  0xabc62248,0xb1edb01d,0xb3eab33b,0xb33bb3ea,0xb26d31ed,0xb33b32dd,0xb3c33388,0xb3fe33ea,0xb3c331ed,0xb1ed33c3,0x28b22d64,0x333bb0c4,
  0xb3ea31ed,0x2d64301d,0x32ddb388,0xb15fa8b2,0xb2dd31ed,0x33feabc6,0xb26dad64,0x2d64326d,0xb0c431ed,0x2ed7b2dd,0xabc63388,0x2248b3ea,
  0xabc631ed,0xb15fb3c3,0x33ea2d64,0xaed730c4,0x28b231ed,0xb388b01d,0xb01db388,0x31ed28b2,0x301d31ed,0xa2482bc6,0xb0c4ad64,0xb388b26d,
  0xb3ea33fe,0xb38833c3,0xb2dd333b,0xb1ed326d,0x32ddb3fe,0x2248b01d,0xb26d2ed7,0xb38833ea,0xb0c433fe,0x333babc6,0x2bc6b33b,0xb3fe30c4,
  0x2bc6b3fe,0xb1ed32dd,0x33eaaed7,0xb33ba8b2,0x28b233fe,0xad64b3c3,0x301d333b,0xb15fb26d,0xb01db3fe,0x33fe301d,0xb0c42ed7,0xad64b3ea,
  0x326d33fe,0xaed72bc6,0xb3c3b33b,0x2248b0c4,0xb3c3b3fe,0xb15fb2dd,0xa8b2aed7,0x2ed728b2,0x29ed29ed,0x29ed29ed,0x29ed29ed,0x29ed29ed,
  0x2bc32a6d,0x2add2bea,0x23c628c4,0xa81da0b2,0x2bc32add,0xa3c6281d,0xabc3aadd,0x23c6a81d,0x29ed2b3b,0xabfea564,0x295fa6d7,0x1a482b88,
  0x25642b88,0xa564ab88,0x25642b88,0xa564ab88,0xa0b22bc3,0x2a6daadd,0xabea23c6,0x28c4281d,0xa8c42bea,0x2a6da0b2,0x28c4abea,0xaa6d20b2,
  0xab3b2bfe,0xa564295f,0x26d79a48,0x2b88a9ed,0x29ed29ed,0x29ed29ed,0x29ed29ed,0x29ed29ed,0xabc3aa6d,0xaaddabea,0xa3c6a8c4,0x281d20b2,
  0x2bc32add,0xa3c6281d,0xabc3aadd,0x23c6a81d,0xa9edab3b,0x2bfe2564,0xa95f26d7,0x9a48ab88,0x25642b88,0xa564ab88,0x25642b88,0xa564ab88,
  0x20b2abc3,0xaa6d2add,0x2beaa3c6,0xa8c4a81d,0xa8c42bea,0x2a6da0b2,0x28c4abea,0xaa6d20b2,0x2b3babfe,0x2564a95f,0xa6d71a48,0xab8829ed,
  0x295f295f,0x295f295f,0x295f295f,0x295f295f,0x23c628c4,0xa81da0b2,0xabc3aa6d,0xaaddabea,0xa3c6281d,0xabc3aadd,0x23c6a81d,0x2bc32add,
  0xa95f26d7,0x9a48ab88,0x29ed2b3b,0xabfea564,0xab882564,0x2b88a564,0xab882564,0x2b88a564,0xabea23c6,0x28c4281d,0x20b2abc3,0xaa6d2add,
  0xaa6d20b2,0xa8c42bea,0x2a6da0b2,0x28c4abea,0xa6d71a48,0xab8829ed,0xab3b2bfe,0xa564295f,0x295f295f,0x295f295f,0x295f295f,0x295f295f,
  0xa3c6a8c4,0x281d20b2,0x2bc32a6d,0x2add2bea,0xa3c6281d,0xabc3aadd,0x23c6a81d,0x2bc32add,0x295fa6d7,0x1a482b88,0xa9edab3b,0x2bfe2564,
  0xab882564,0x2b88a564,0xab882564,0x2b88a564,0x2beaa3c6,0xa8c4a81d,0xa0b22bc3,0x2a6daadd,0xaa6d20b2,0xa8c42bea,0x2a6da0b2,0x28c4abea,
  0x26d79a48,0x2b88a9ed,0x2b3babfe,0x2564a95f,0xabfe2bfe,0xabfe2bfe,0xabfe2bfe,0xabfe2bfe,0xaadd2bea,0xa3c628c4,0x281da0b2,0x2bc3aa6d,
  0xa81d2bc3,0x2adda3c6,0x281dabc3,0xaadd23c6,0x9a482b88,0x29edab3b,0xabfe2564,0x295f26d7,0x26d72b3b,0xa6d7ab3b,0x26d72b3b,0xa6d7ab3b,
  0x2a6d2add,0xabeaa3c6,0x28c4a81d,0x20b22bc3,0x2bea2a6d,0xa0b228c4,0xabeaaa6d,0x20b2a8c4,0x2b8829ed,0x2b3b2bfe,0x2564295f,0xa6d79a48,
  0xabfe2bfe,0xabfe2bfe,0xabfe2bfe,0xabfe2bfe,0x2addabea,0x23c6a8c4,0xa81d20b2,0xabc32a6d,0xa81d2bc3,0x2adda3c6,0x281dabc3,0xaadd23c6,
  0x1a48ab88,0xa9ed2b3b,0x2bfea564,0xa95fa6d7,0x26d72b3b,0xa6d7ab3b,0x26d72b3b,0xa6d7ab3b,0xaa6daadd,0x2bea23c6,0xa8c4281d,0xa0b2abc3,
  0x2bea2a6d,0xa0b228c4,0xabeaaa6d,0x20b2a8c4,0xab88a9ed,0xab3babfe,0xa564a95f,0x26d71a48,0x1a489a48,0x1a489a48,0x1a489a48,0x1a489a48,
  0x281da0b2,0x2bc3aa6d,0x2addabea,0x23c6a8c4,0x2adda3c6,0x281dabc3,0xaadd23c6,0xa81d2bc3,0x2bfea564,0xa95fa6d7,0x9a482b88,0x29edab3b,
  0x2b3ba6d7,0xab3b26d7,0x2b3ba6d7,0xab3b26d7,0x28c4a81d,0x20b22bc3,0xaa6daadd,0x2bea23c6,0x20b2a8c4,0x2bea2a6d,0xa0b228c4,0xabeaaa6d,
  0xa564a95f,0x26d71a48,0x2b8829ed,0x2b3b2bfe,0x1a489a48,0x1a489a48,0x1a489a48,0x1a489a48,0xa81d20b2,0xabc32a6d,0xaadd2bea,0xa3c628c4,
  0x2adda3c6,0x281dabc3,0xaadd23c6,0xa81d2bc3,0xabfe2564,0x295f26d7,0x1a48ab88,0xa9ed2b3b,0x2b3ba6d7,0xab3b26d7,0x2b3ba6d7,0xab3b26d7,
  0xa8c4281d,0xa0b2abc3,0x2a6d2add,0xabeaa3c6,0x20b2a8c4,0x2bea2a6d,0xa0b228c4,0xabeaaa6d,0x2564295f,0xa6d79a48,0xab88a9ed,0xab3babfe,
  0xa95fa95f,0xa95fa95f,0xa95fa95f,0xa95fa95f,0xa3c6a8c4,0x281d20b2,0x2bc32a6d,0x2add2bea,0x23c6a81d,0x2bc32add,0xa3c6281d,0xabc3aadd,
  0x295fa6d7,0x1a482b88,0xa9edab3b,0x2bfe2564,0x2b88a564,0xab882564,0x2b88a564,0xab882564,0x2beaa3c6,0xa8c4a81d,0xa0b22bc3,0x2a6daadd,
  0x2a6da0b2,0x28c4abea,0xaa6d20b2,0xa8c42bea,0x26d79a48,0x2b88a9ed,0x2b3babfe,0x2564a95f,0xa95fa95f,0xa95fa95f,0xa95fa95f,0xa95fa95f,
  0x23c628c4,0xa81da0b2,0xabc3aa6d,0xaaddabea,0x23c6a81d,0x2bc32add,0xa3c6281d,0xabc3aadd,0xa95f26d7,0x9a48ab88,0x29ed2b3b,0xabfea564,
  0x2b88a564,0xab882564,0x2b88a564,0xab882564,0xabea23c6,0x28c4281d,0x20b2abc3,0xaa6d2add,0x2a6da0b2,0x28c4abea,0xaa6d20b2,0xa8c42bea,
  0xa6d71a48,0xab8829ed,0xab3b2bfe,0xa564295f,0x29ed29ed,0x29ed29ed,0x29ed29ed,0x29ed29ed,0x2bc32a6d,0x2add2bea,0x23c628c4,0xa81da0b2,
  0x2bc32add,0xa3c6281d,0xabc3aadd,0x23c6a81d,0x29ed2b3b,0xabfea564,0x295fa6d7,0x1a482b88,0x25642b88,0xa564ab88,0x25642b88,0xa564ab88,
  0xa0b22bc3,0x2a6daadd,0xabea23c6,0x28c4281d,0xa8c42bea,0x2a6da0b2,0x28c4abea,0xaa6d20b2,0xab3b2bfe,0xa564295f,0x26d79a48,0x2b88a9ed,
  0x29ed29ed,0x29ed29ed,0x29ed29ed,0x29ed29ed,0xabc3aa6d,0xaaddabea,0xa3c6a8c4,0x281d20b2,0x2bc32add,0xa3c6281d,0xabc3aadd,0x23c6a81d,
  0xa9edab3b,0x2bfe2564,0xa95f26d7,0x9a48ab88,0x25642b88,0xa564ab88,0x25642b88,0xa564ab88,0x20b2abc3,0xaa6d2add,0x2beaa3c6,0xa8c4a81d,
  0xa8c42bea,0x2a6da0b2,0x28c4abea,0xaa6d20b2,0x2b3babfe,0x2564a95f,0xa6d71a48,0xab8829ed,0x9a481a48,0x9a481a48,0x9a481a48,0x9a481a48,
  0xa81d20b2,0xabc32a6d,0xaadd2bea,0xa3c628c4,0xaadd23c6,0xa81d2bc3,0x2adda3c6,0x281dabc3,0xabfe2564,0x295f26d7,0x1a48ab88,0xa9ed2b3b,
  0xab3b26d7,0x2b3ba6d7,0xab3b26d7,0x2b3ba6d7,0xa8c4281d,0xa0b2abc3,0x2a6d2add,0xabeaa3c6,0xa0b228c4,0xabeaaa6d,0x20b2a8c4,0x2bea2a6d,
  0x2564295f,0xa6d79a48,0xab88a9ed,0xab3babfe,0x9a481a48,0x9a481a48,0x9a481a48,0x9a481a48,0x281da0b2,0x2bc3aa6d,0x2addabea,0x23c6a8c4,
  0xaadd23c6,0xa81d2bc3,0x2adda3c6,0x281dabc3,0x2bfea564,0xa95fa6d7,0x9a482b88,0x29edab3b,0xab3b26d7,0x2b3ba6d7,0xab3b26d7,0x2b3ba6d7,
  0x28c4a81d,0x20b22bc3,0xaa6daadd,0x2bea23c6,0xa0b228c4,0xabeaaa6d,0x20b2a8c4,0x2bea2a6d,0xa564a95f,0x26d71a48,0x2b8829ed,0x2b3b2bfe,
  0xabfe2bfe,0xabfe2bfe,0xabfe2bfe,0xabfe2bfe,0xaadd2bea,0xa3c628c4,0x281da0b2,0x2bc3aa6d,0xa81d2bc3,0x2adda3c6,0x281dabc3,0xaadd23c6,
  0x9a482b88,0x29edab3b,0xabfe2564,0x295f26d7,0x26d72b3b,0xa6d7ab3b,0x26d72b3b,0xa6d7ab3b,0x2a6d2add,0xabeaa3c6,0x28c4a81d,0x20b22bc3,
  0x2bea2a6d,0xa0b228c4,0xabeaaa6d,0x20b2a8c4,0x2b8829ed,0x2b3b2bfe,0x2564295f,0xa6d79a48,0xabfe2bfe,0xabfe2bfe,0xabfe2bfe,0xabfe2bfe,
  0x2addabea,0x23c6a8c4,0xa81d20b2,0xabc32a6d,0xa81d2bc3,0x2adda3c6,0x281dabc3,0xaadd23c6,0x1a48ab88,0xa9ed2b3b,0x2bfea564,0xa95fa6d7,
  0x26d72b3b,0xa6d7ab3b,0x26d72b3b,0xa6d7ab3b,0xaa6daadd,0x2bea23c6,0xa8c4281d,0xa0b2abc3,0x2bea2a6d,0xa0b228c4,0xabeaaa6d,0x20b2a8c4,
  0xab88a9ed,0xab3babfe,0xa564a95f,0x26d71a48,0x3bfb3bff,0x3be53bf2,0x3bbf3bd4,0x3b873ba5,0x3bd03bfb,0x3b013b7c,0x399d3a60,0x378538bc,
  0x35173b52,0xbbc9b7c8,0xb074ba9b,0x3bfe391b,0x319e3b27,0xbbf3b979,0x363cb80a,0x3a2d3bc5,0xba093986,0x3a7eb8f8,0xbae5385f,0x3b3db77a,
  0xbabd393c,0x3bb0b699,0xbc00305b,0x3ba730d7,0xbb2a35c8,0xb8353bb2,0x3a64b1e8,0x3962bbf7,0xba90350b,0xba413bff,0x3602340e,0x3bf6bad8,
  0xac6aa5e4,0xb122af59,0xb402b294,0xb56ab4b7,0xb2deac9c,0xb7bdb5a5,0xb9b3b8d6,0xbb10ba73,0xbb96b676,0xb359bafe,0x3bec3884,0x2a163a29,
  0xbbe0b72c,0x2f27b9d6,0x3b5e3ae8,0xb91633a2,0xb941b9c9,0x38ad3a45,0xb80fbab3,0x36d23b13,0xb850ba0d,0x346f3b4a,0x1fdbbbed,0xb4ab3be8,
  0x3721bb76,0xbace3463,0xb8d13bdd,0x39ebadfb,0x3894bb98,0xb8fd281f,0xbb6a3bbd,0x2e2d3825,0x3b3f3b65,0x3ae83b16,0x3a813ab6,0x3a0d3a49,
  0x3263356a,0xad972b43,0xb5dfb359,0xb8eeb7f3,0xa9b139aa,0xbbedba25,0x3340b889,0x3b983afb,0xbaa2aa16,0xb4cfbb8e,0x3c0038ad,0xb44b38e5,
  0xbb853625,0x3bbdb4c3,0xbbe432ad,0x3bfbaf8b,0xbaacb6d2,0x39243954,0xb65fbace,0x2fbd3bb8,0xb9661648,0xba603bf8,0x383a31cf,0x3b27bbb3,
  0x3219b9eb,0xbb1836f4,0xb9903be5,0x37dd3010,0xb6c6b61a,0xb80ab76f,0xb8a8b85a,0xb93cb8f3,0xbbd7bb87,0xbbf8bbfd,0xbb71bbc9,0xba4dbaf1,
  0xbbfeb9a6,0x305bb91f,0x3bcb3a97,0xb50b37d2,0xb87abbfe,0x3ba13546,0x24523a7e,0xbbb5ba54,0xb576bb63,0x340e3ba3,0xb13bbbd3,0x2c9c3bf2,
  0x386abb3d,0xba2139f8,0x3b57b835,0xbbf13432,0x39e7bc00,0xb8d6adc9,0xbacb3bde,0x372c3457,0x3bdab962,0x3764bb35,0xb9c03122,0xbaf73bef,
  0x398b39cd,0x38fd3946,0x386538b2,0x37853815,0xba85b9c9,0xbb92bb1e,0xbbfebbdd,0xbbc2bbf5,0xb66b3682,0xbb01bb94,0x387fb371,0x3a2d3beb,
  0xbac7bb76,0x3a00ad33,0x36bb3bd4,0xbbeab79b,0xbc0026ad,0x3bf32c38,0xbbd6b109,0x3ba733eb,0x3153bbff,0xb70a3b9e,0x396bba9b,0xbade390c,
  0xb5d4b5bc,0xbbb03b2c,0x32013830,0x3bf6ba67,0x3bccbb52,0x2c06b92e,0xbb83385f,0xb8c73bab,0xb9c5b982,0xba41ba04,0xbab0ba7a,0xbb10bae1,
  0xb8a3b986,0xb52fb74e,0xa94db1e8,0x33d32e91,0xbb54bb4f,0x37bdb523,0x3a9e3bc8,0xb916308d,0x3840b5c8,0x394a3bf9,0xbb42b294,0xb0a6bb0a,
  0x251bbbff,0xaf273bfc,0x327cbbe6,0xb4ab3bc0,0x3be325e4,0xbb2fb4e7,0x39e33884,0xb81aba35,0x3b73bb78,0xb46fb715,0xbbdc3ad1,0x2e2d38cc,
  0x33283676,0x3bfcba19,0x3581bab3,0xba6b3493,0x363136dd,0x34cf3581,0x32c6341a,0x2fbd3153,0xbae1bb65,0xb970ba39,0xb715b889,0xb16cb4f3,
  0xb9a12a7a,0xb924bbfe,0x3a933042,0x37dd3bcc,0x308db9aa,0x3b453b07,0xb94632ad,0xb845bbfa,0xbb68b55e,0x3b1836bb,0xbabab805,0x3a4d38a3,
  0x3bc0b625,0xbbfe2ec3,0x3b9431cf,0xba89b742,0x9cb6b95d,0xbbf8396b,0xb1b63a5c,0x3bb5b840,0x38cc9648,0x3b81bbac,0xac38b85a,0xbbce3933,
  0xbb60bb3a,0xbba1bb83,0xbbd2bbbc,0xbbf1bbe3,0x3815361a,0x39df3907,0x3b2c3a97,0x3be23b9c,0xb9afbbfd,0x3a21294d,0x388e3bee,0xbaf7b328,
  0x3beb39a6,0xb6af37a6,0xba04bbd3,0x3ac42d00,0x360ebb89,0xb7643b42,0x3855baeb,0xb8ee3a85,0x33eb3b63,0x28e8bbf5,0xb5233bde,0x389ebb21,
  0x3c00b9f0,0x2d97b9e3,0xbbdf38db,0xb44b3ac7,0xba673c00,0x358d3487,0x3bfcbab6,0x330fba15,0x3b7a3bf1,0x394a3a93,0x33893764,0xb3d39cb6,
  0x3afb3be2,0x35eb3946,0xb4c328e8,0xbaa9b8cc,0x27763af7,0xbb2fbaba,0x3a76ad97,0x30a63b60,0xaf8b3ac4,0xb994bb94,0x3bf8358d,0xb8743815,
  0xbb4c38ee,0x3bfcb1b6,0xbad5b4cf,0x381a39af,0xbbb3389e,0x3b592c38,0xb76fb970,0xb24b3beb,0xb9d2344b,0xbb923bd2,0xb0f03924,0x3a6bb60e,
  0xb8f3330f,0xbc003b2c,0xb91f3b45,0x323233eb,0xb5b1afbd,0xba00b88e,0xbbc6bb18,0xbbc2bc00,0xb7d2b16c,0xbb6fba04,0xbba3bbfe,0xb86fba67,
  0xbbffb7dd,0x370ab855,0x38b73bf8,0xbbeab631,0xbbf2b845,0x39bcb523,0x2dc93b81,0xbaa5bae1,0xb68dba4d,0xac063bdf,0x382abba1,0xbade39a1,
  0xb457ba89,0xb6543bfc,0x3b16b9df,0xbbd8308d,0x397dbbb5,0xb52fb2c6,0xbbe73a21,0xb8c73b68,0x3a49bbce,0x2311b715,0xba2536af,0xbbd93bc0,
  0xb958b785,0xbb81ba9e,0xbbefbbf3,0xba89bb73,0xbbf7bbc2,0xb9b8bb42,0xaf59b70a,0x384a3328,0xbb8bba2d,0x39dfb27c,0x34263bb0,0xbbceb98b,
  0xb4b7bbea,0x3b6c39e3,0xbafe2c06,0x3185ba85,0xaadebba7,0xb6af3bdc,0x3a58ba41,0xbbe2366b,0x3a29bade,0xbc003581,0x3a45352f,0xb2f7bac7,
  0x3b37bbf6,0x28e8b865,0xbaee37bd,0xbac43c00,0x3b13b8c7,0x3b5cbbfe,0x3463b94a,0xb8993153,0xb9f4bb10,0xb58db87f,0x3029af27,0x389e35d4,
  0x2dfbb3d3,0x399936bb,0x3bf23b2f,0x3ac13bcc,0x3552b916,0x39703bd6,0xbbbab46f,0x330fb9c5,0x3ba530a6,0xb5f7396b,0xb7c8bbfc,0x3be138a3,
  0x3bfdb4ab,0xbb45b201,0x38e038fd,0xb16cbb54,0x391b381a,0xa17fbb83,0xb8f83b92,0x3bcfb840,0x36e82e2d,0x3bfebab0,0x37febb01,0xb845251b,
  0xb77a3a6b,0x3648294d,0x3bb2ba00,0x3a8cbbe3,0xb742b93c,0x2311b340,0x37a6340e,0x3aa93966,0x3b963a4d,0x3b7f3c00,0x380f3a21,0xb0be3219,
  0x3933b50b,0x35eb3be4,0xbbf5b8d6,0x3874b6c6,0x39413bb5,0xbbffb65f,0x38d1b764,0x33ba3bd7,0x3b9c2c9c,0xb994b83a,0x34873ae8,0x324bbbfe,
  0xb7213bf1,0x3b47b990,0xbbbf2d97,0x38c1387a,0x2d00372c,0x3b59b8a8,0x3a39bbed,0xb232b576,0xbbfb3af7,0xb9743b71,0x307434cf,0x3adbb86a,
  0x3b213a0d,0x3c003bcb,0x3b073bbd,0x386f39e7,0x351738ee,0xb599a452,0xbae5b924,0xbbe9bbda,0x3a153b98,0xbb6fb13b,0x2ec3ba60,0x3aa53b3f,
  0xba09344b,0xa884bb57,0x3a643b18,0xbbc3b263,0xb4f33bfb,0x39bcbacb,0xbbac380a,0x3bd8a9b1,0xbb2aafbd,0x36a439c0,0x3402bbf8,0xba6f3aa2,
  0xbbfa3b27,0xb6543a81,0x3907b05b,0x3bd9bb85,0x2c6ab7dd,0xb9da35df,0xbbec3ba1,0xb8203aac,0x3bf53b87,0x3b6c3bec,0x392e3a7e,0x32f73721,
  0xb9e7b785,0xbbfcbb5e,0xba81bbb0,0xb43eb894,0x379b3bfe,0xbc00b80f,0x374eb835,0x38993bfb,0xbb3fba2d,0x3b329fdb,0xb3403a41,0xb8eabbd0,
  0xb90c3b3d,0x3b5cb8d1,0xbbf93122,0x3ac13517,0x29b1bba7,0xb94f3b6a,0x3be4b7bd,0xbaf4b19e,0xbbab3962,0xb9993bbf,0x34e73359,0x3be1ba09,
  0x3b85bbf6,0x353ab99d,0xb83a2f27,0xbbf03abd,0x2e91356a,0xb5f7b074,0xba19b8ad,0xbbcfbb2a,0xb966bb10,0xaba7b63c,0x38a8346f,0x3bb73a90,
  0xbb0aaa16,0xa17fbae5,0x3b1e3ace,0xba8c2c6a,0x36c6b916,0x36ff3c00,0xbbcbb8fd,0x3a50b2de,0xba35b6d2,0x36483a64,0x2d33bbe5,0xb84a3b96,
  0x3bfeb4ab,0xb9fcb602,0x313b3b01,0x37e8bbe0,0x3493b9eb,0xb9b83402,0xbb9e3bc9,0xb1853941,0x35762e2d,0x3b90b9b3,0x3acbbbf3,0x2fefb850,
  0x3a543bcf,0x2884374e,0xb9f8b648,0xbbe9bbab,0x398b3bb7,0xb4db3340,0xbbdcb9fc,0xb911bb85,0xb4323a8c,0xb6a4bbf9,0x3b3539b8,0xbbc3ae91,
  0xb66b3a50,0xad65bbe4,0x38653b90,0xbb0db966,0xbbef384a,0x39da34e7,0x2b43bb6c,0xba6f3b0a,0xbc0037e8,0x3759383a,0x387fbbfc,0xbbf636c6,
  0xb7f33185,0xbb7f3a19,0xbb8e3c00,0xb8203a35,0xb5d42fef,0xba1d38a8,0xbbd63b32,0xbba93bfe,0xb8e5b2f7,0xbbffbb1e,0xb954bb5c,0x30beb493,
  0xb9c5b43e,0xbb9fbbcb,0xb201b94f,0x3a313576,0xbbb8b899,0x3b47ad33,0xb6f43999,0xb3babbf5,0xbb54b8ea,0x3bf9313b,0xbab0353a,0x3790b9e7,
  0xb010bac1,0xb9743b9e,0x3bfdb5f7,0xb8c1b79b,0x251bbaf4,0xbb1b3acb,0x3a9e2ba7,0x2e5fbb3f,0x3af1bbe1,0x3599b92e,0xb546a17f,0xbadb390c,
  0x3b73bbf0,0x3929ba81,0x327cb6ff,0xb49f29b1,0xb825baa9,0x353aaec3,0x3b7c3994,0x3af43bfa,0x360eb0be,0x3bf43a64,0x388e3b47,0xb7372c6a,
  0x38bcb874,0x2ba73bac,0xb979bb59,0x3bf03742,0x3c0033ba,0xbb043402,0x3855b974,0xacce3b96,0x3bc5b24b,0xb6ffb907,0xb6993c00,0x3bb7b933,
  0x363138c1,0x3902bbec,0xbbdf3599,0x34ff3941,0x30d73232,0x39fcb7a6,0x3bffbb6f,0x3a50bb9c,0xb9a13adb,0xb47b380f,0x32c62884,0x3937b721,
  0x3ad8386f,0x3b903bf5,0x35a539bc,0xb7e8ad00,0x3b683be9,0x2ef538d1,0xba93b6a4,0xbb24bbfb,0x3a733aa5,0xbbfcb487,0x39d6b654,0xafef3b21,
  0x1cb63bc3,0xb7b2bbbf,0x3aba39da,0xbbfab517,0xb3a23bd8,0x3b32ba39,0xbb4a2311,0x343e3a15,0xbb603a6f,0x3a3d3074,0x31b6bb7f,0xbb9a3a09,
  0xbbe83bd9,0xb94f3b07,0xa81f35eb,0x38eab4f3,0xb9af3820,0xbbae3ae5,0xbbd23bff,0xba113b2a,0x319e389e,0xb929b426,0xbc00bb45,0xb911bb37,
  0xbbffbac1,0xb805bafe,0x382a217f,0x3bfd3b13,0xbabd330f,0x34dbba58,0x36023bfe,0xbb0db9f4,0xb68dbbe1,0x3a5c3a45,0xbbe7b648,0x3b89adfb,
  0xba90b16c,0x2d653aee,0x39b3bb81,0xbbf63552,0x397dbbcf,0xbbbc3463,0x338939b8,0x39f0bba5,0x32deb845,0xb7593029,0xbb5e39df,0xbba93bfd,
  0x3b7aba8c,0x3beebbf2,0x3a76bb6c,0x36ddb91b,0xbbe0ba89,0xba1dbbba,0x1fdbb6af,0x3a3136e8,0xa776b84a,0x3aeb37c8,0x3ad53c00,0xaa7a377a,
  0xb850bbce,0x3b9f38e0,0xbb6a28e8,0x3790b958,0x3b4cb185,0xb8db38f8,0x30f0bb5c,0x355e3bf7,0x3894bbe2,0xbbf937fe,0x399d358d,0x2e5fbb8b,
  0x39d232f7,0x341abbb2,0xbbc63999,0x395d34b7,0x3bd0bac4,0x3b1bbbef,0x363cb970,0xb49faade,0xb5b13899,0x30422f59,0x38b7b5f7,0x3b3aba29,
  0x3219b3d3,0x3b0438b7,0x3b713bfc,0x34ff397d,0x36e83aa9,0xb8b2adc9,0xbbefbb59,0xb5bcba49,0x3bd730a6,0xb902382a,0xa452bb92,0x39373b7a,
  0xb9583874,0x3371bb16,0x34263c00,0xb982bafb,0x387a381a,0x347bbbe7,0xbb573a00,0x3b242776,0xbb8b324b,0x31093a25,0x3a58bb6f,0xbb4f2f8b,
  0xb86a3a6b,0x2ef53389,0x39c0b70a,0x3bfabb4c,0xaadeb232,0xb83034c3,0xbaee39bc,0xbbff3bb3,0x3bda3bc2,0x37b23a76,0xb5df2c06,0xbb9ab9d2,
  0xbb37b86f,0xba7abbf8,0x3029b654,0x3b7838f3,0x32633bea,0xba3dbad5,0x3c00352f,0xba1135b1,0xb9f4baa5,0x3bc8376f,0xbbba2311,0x39cdb7d2,
  0xbaa23ade,0x3baeb0f0,0xb65fb94a,0xb7373bff,0x3552bbd8,0xbbe6391f,0x38e035eb,0x3682bbf2,0xbaac38c7,0xbbf43bc6,0xb9903b2f,0xacce368d,
  0x3bfdbbd9,0x3ad1bba3,0x37feb994,0x26adb457,0x38a33b9a,0xb8dba452,0xbb83bbae,0x2a7ab86a,0x37423b78,0xbab6b426,0xb907bbe6,0x39aa2ade,
  0xb8403a11,0x341abb57,0x294d3bf4,0xb55ebbda,0xb93339cd,0x3889ba58,0xb7a63ad1,0x3625bb37,0xbbe33737,0x304239c0,0x3b42bb04,0xb95db263,
  0xbb9c3682,0xb2ad3aee,0x3bf5b8b2,0x1648b9f4,0xb3282cce,0xb80535df,0xb9e33902,0xbb3a3aa2,0xad0026ad,0xb1cf3029,0xb4873371,0xb61a3552,
  0xba85b4ff,0xba5cbc00,0x3581b47b,0x3bfd3aac,0xbb21b5bc,0xb85abbba,0x3a393109,0x39a63bfd,0xbac7b937,0x3bbc365f,0xbbfeaef5,0x3b89b219,
  0xba15b982,0x3a9738e0,0xbb07b830,0x3b6336e8,0x3153bb24,0xbbee3990,0x36bb37b2,0x39f0bbd7,0x34f3bb4f,0xbbd337fe,0xaec33a7a,0x3c00b958,
  0x3bccbbfa,0x3aebbb71,0x396bba3d,0x36ddb87a,0x3bfabbff,0x3bdebbef,0x3bacbbc8,0x3b65bb8b,0x3bc03911,0x38303b6a,0xb946ad65,0xbb4fbbd0,
  0x3a353bfd,0xb85f30f0,0xbb1ebbbc,0x35c8b5b1,0x38cc3b0d,0xba7ab99d,0x3b943759,0xbbffb19e,0xb4933b89,0x31e8bbc6,0xad333bee,0xa5e4bbff,
  0xb8153bf6,0x3bc8b63c,0xac38ba1d,0xbb783abd,0xbbf539f0,0x329438b7,0x3b9ebaeb,0xb676b68d,0xbbeb3ba9,0xbbe63c00,0xbb2c3b9f,0xb9cd3a90,
  0xb79b36dd,0xb884382a,0xb92e38db,0xb9c9397d,0x33eb3a31,0xbad1b602,0xba04bbf9,0x3682b2de,0xb90c2a7a,0xbab3bbe7,0x374eb41a,0x3b763b7a,
  0xba673790,0x38b2b9b3,0xb5233b1b,0x26adbbe0,0xbbabb55e,0x3bdd3389,0xbbf9b042,0x3bff2776,0xbae12e5f,0xb3713b5e,0x3bfcb929,0xb5bcb850,
  0xae91b95d,0xbbd43a76,0x34e73805,0x3b52bb4c,0x308db49f,0xb1091fdb,0xb71534db,0xb9823894,0x3b0abb3a,0x3a9bbad5,0x3a19ba5c,0x3986b9d2,
  0x2f8bb7e8,0x3bde3979,0x376f3b32,0xb9aab0d7,0x3bb83b24,0xb1223855,0xbbfdba3d,0xaa16b9a1,0x3bb3afef,0xbab63699,0x391fb94f,0xb6253ad8,
  0x30103bfa,0xb359bbdf,0x35463bae,0xb6d2bb68,0x38f3343e,0x3889bbff,0xbba3353a,0x96483a73,0xbaf13b9a,0x38ad32c6,0x39f8bbf4,0xb9eb9cb6,
  0xb7d238ea,0xb2ad35a5,0x2dc92ba7,0x361ab3a2,0xba543a11,0xbace3a93,0xbb353b04,0xbb873b60,0x3bf23af4,0x31cf39d6,0xbb16b6ff,0xb9a6bbe8,
  0xb4323737,0xbbe5baba,0x2b43b902,0x3bfe39af,0x34573bf0,0xb85abb4a,0x3a2539fc,0xbb63b825,0xbbef2cce,0x3bc9b1b6,0xbb8e347b,0x3b3db60e,
  0xba493bb7,0x3a97a81f,0x34c3bb90,0xbc0038bc,0xb7f3b4ff,0xba7e3bd2,0x39542ef5,0x3962bc00,0xbafb3a50,0xbbd33b7c,0xbbf83bfc,0xbb653bc5,
  0x38e5b937,0x3835b88e,0x36f4b7b2,0x356ab631,0xbb13bbe9,0x31e8b6f4,0x3bf239da,0x36763af1,0x3be83911,0x340e3ab0,0xbb7cb759,0xb72cbb73,
  0x2dfbbbc3,0x32943bfd,0xb7c8bb7f,0x39c93a54,0x38253b0d,0xb8d6ba9e,0x39793a1d,0xba0db98b,0x3ba5ba6f,0xb884b546,0xb8f83bff,0x3b76b432,
  0xb8bc3bf6,0x3ae8b27c,0x3699bb9f,0xbb98366b,0x391bb820,0x3ab3b9f8,0x3bb2bb47,0x3bffbbef,0xbbc53ba9,0xbbed3bdc,0xbbff3bf9,0xbbfb3c00,
  0x377ab0be,0x3bdd3b35,0x2f593974,0xbb52b7f3,0x30d73a31,0xbbbdb865,0xb5a5bb1b,0x3b2735d4,0x3bf733ba,0xbbd42b43,0x3afeb599,0xb98638e5,
  0xbad83790,0x3a60b87f,0xb9d63929,0x393cb9c5,0x34b738c1,0x3a9bbb8e,0xba45a884,0xb5c83bb8,0xba732e5f,0xb80a3bd6,0x3b4ab4db,0x350bbb54,
  0xba293adb,0xb85f3954,0xb46336a4,0x25e43010,0x33a2b49f,0x305bb201,0x281fad65,0xac9c251b,0x3f803f80,0x3f803f80,0x3f803f80,0x3f803f80,
  0x3f803f80,0x3f803f80,0x3f803f80,0x3f803f80,0x3f803f80,0x3f803f80,0x3f803f80,0x3f803f80,0x3f803f80,0x3f803f80,0x3f803f80,0x3f803f80,
  0x3f803f80,0x3f803f80,0x3f803f80,0x3f803f80,0x3f803f80,0x3f803f80,0x3f803f80,0x3f803f80,0x3f803f80,0x3f803f80,0x3f803f80,0x3f803f80,
  0x3f803f80,0x3f803f80,0x3f803f80,0x3f803f80,0x3f803f80,0x3f803f80,0x3f803f80,0x3f803f80,0x3f803f80,0x3f803f80,0x3f803f80,0x3f803f80,
  0x3f803f80,0x3f803f80,0x3f803f80,0x3f803f80,0x3f803f80,0x3f803f80,0x3f803f80,0x3f803f80,0x3f803f80,0x3f803f80,0x3f803f80,0x3f803f80,
  0x3f803f80,0x3f803f80,0x3f803f80,0x3f803f80,0x3f803f80,0x3f803f80,0x3f803f80,0x3f803f80,0x3f803f80,0x3f803f80,0x3f803f80,0x3f803f80,
  0x3f803f80,0x3f803f80,0x3f803f80,0x3f803f80,0x3f803f80,0x3f803f80,0x3f803f80,0x3f803f80,0x3f803f80,0x3f803f80,0x3f803f80,0x3f803f80,
  0x3f803f80,0x3f803f80,0x3f803f80,0x3f803f80,0x3f803f80,0x3f803f80,0x3f803f80,0x3f803f80,0x3f803f80,0x3f803f80,0x3f803f80,0x3f803f80,
  0x3f803f80,0x3f803f80,0x3f803f80,0x3f803f80,0x3f803f80,0x3f803f80,0x3f803f80,0x3f803f80,0x3f803f80,0x3f803f80,0x3f803f80,0x3f803f80,
  0x3f803f80,0x3f803f80,0x3f803f80,0x3f803f80,0x3f803f80,0x3f803f80,0x3f803f80,0x3f803f80,0x3f803f80,0x3f803f80,0x3f803f80,0x3f803f80,
  0x3f803f80,0x3f803f80,0x3f803f80,0x3f803f80,0x3f803f80,0x3f803f80,0x3f803f80,0x3f803f80,0x3f803f80,0x3f803f80,0x3f803f80,0x3f803f80,
  0x3f803f80,0x3f803f80,0x3f803f80,0x3f803f80,0x3f803f80,0x3f803f80,0x3f803f80,0x3f803f80,0x3f803f80,0x3f803f80,0x3f803f80,0x3f803f80,
  0x3f803f80,0x3f803f80,0x3f803f80,0x3f803f80,0x3f803f80,0x3f803f80,0x3f803f80,0x3f803f80,0x3f803f80,0x3f803f80,0x3f803f80,0x3f803f80,
  0x3f803f80,0x3f803f80,0x3f803f80,0x3f803f80,0x3f803f80,0x3f803f80,0x3f803f80,0x3f803f80,0x3f803f80,0x3f803f80,0x3f803f80,0x3f803f80,
  0x3f803f80,0x3f803f80,0x3f803f80,0x3f803f80,0x3f803f80,0x3f803f80,0x3f803f80,0x3f803f80,0x3f803f80,0x3f803f80,0x3f803f80,0x3f803f80,
  0x3f803f80,0x3f803f80,0x3f803f80,0x3f803f80,0x3f803f80,0x3f803f80,0x3f803f80,0x3f803f80,0x3f803f80,0x3f803f80,0x3f803f80,0x3f803f80,
  0x3f803f80,0x3f803f80,0x3f803f80,0x3f803f80,0x3f803f80,0x3f803f80,0x3f803f80,0x3f803f80,0x3f803f80,0x3f803f80,0x3f803f80,0x3f803f80,
  0x3f803f80,0x3f803f80,0x3f803f80,0x3f803f80,0x3f803f80,0x3f803f80,0x3f803f80,0x3f803f80,0x3f803f80,0x3f803f80,0x3f803f80,0x3f803f80,
  0x3f803f80,0x3f803f80,0x3f803f80,0x3f803f80,0x3f803f80,0x3f803f80,0x3f803f80,0x3f803f80,0x3f803f80,0x3f803f80,0x3f803f80,0x3f803f80,
  0x3f803f80,0x3f803f80,0x3f803f80,0x3f803f80,0x3f803f80,0x3f803f80,0x3f803f80,0x3f803f80,0x3f803f80,0x3f803f80,0x3f803f80,0x3f803f80,
  0x3f803f80,0x3f803f80,0x3f803f80,0x3f803f80,0x3f803f80,0x3f803f80,0x3f803f80,0x3f803f80,0x3f803f80,0x3f803f80,0x3f803f80,0x3f803f80,
  0x3f803f80,0x3f803f80,0x3f803f80,0x3f803f80,0x3f803f80,0x3f803f80,0x3f803f80,0x3f803f80,0x3f803f80,0x3f803f80,0x3f803f80,0x3f803f80,
  0x3f803f80,0x3f803f80,0x3f803f80,0x3f803f80,0x3f803f80,0x3f803f80,0x3f803f80,0x3f803f80,0x3f803f80,0x3f803f80,0x3f803f80,0x3f803f80,
  0x3f803f80,0x3f803f80,0x3f803f80,0x3f803f80,0x3f803f80,0x3f803f80,0x3f803f80,0x3f803f80,0x3f803f80,0x3f803f80,0x3f803f80,0x3f803f80,
  0x3f803f80,0x3f803f80,0x3f803f80,0x3f803f80,0x3f803f80,0x3f803f80,0x3f803f80,0x3f803f80,0x3f803f80,0x3f803f80,0x3f803f80,0x3f803f80,
  0x3f803f80,0x3f803f80,0x3f803f80,0x3f803f80,0x3f803f80,0x3f803f80,0x3f803f80,0x3f803f80,0x3f803f80,0x3f803f80,0x3f803f80,0x3f803f80,
  0x3f803f80,0x3f803f80,0x3f803f80,0x3f803f80,0x3f803f80,0x3f803f80,0x3f803f80,0x3f803f80,0x3f803f80,0x3f803f80,0x3f803f80,0x3f803f80,
  0x3f803f80,0x3f803f80,0x3f803f80,0x3f803f80,0x3f803f80,0x3f803f80,0x3f803f80,0x3f803f80,0x3f803f80,0x3f803f80,0x3f803f80,0x3f803f80,
  0x3f803f80,0x3f803f80,0x3f803f80,0x3f803f80,0x3f803f80,0x3f803f80,0x3f803f80,0x3f803f80,0x3f803f80,0x3f803f80,0x3f803f80,0x3f803f80,
  0x3f803f80,0x3f803f80,0x3f803f80,0x3f803f80,0x3f803f80,0x3f803f80,0x3f803f80,0x3f803f80,0x3f803f80,0x3f803f80,0x3f803f80,0x3f803f80,
  0x3f803f80,0x3f803f80,0x3f803f80,0x3f803f80,0x3f803f80,0x3f803f80,0x3f803f80,0x3f803f80,0x3f803f80,0x3f803f80,0x3f803f80,0x3f803f80,
  0x3f803f80,0x3f803f80,0x3f803f80,0x3f803f80,0x3f803f80,0x3f803f80,0x3f803f80,0x3f803f80,0x3f803f80,0x3f803f80,0x3f803f80,0x3f803f80,
  0x3f803f80,0x3f803f80,0x3f803f80,0x3f803f80,0x3f803f80,0x3f803f80,0x3f803f80,0x3f803f80,0x3f803f80,0x3f803f80,0x3f803f80,0x3f803f80,
  0x3f803f80,0x3f803f80,0x3f803f80,0x3f803f80,0x3f803f80,0x3f803f80,0x3f803f80,0x3f803f80,0x3f803f80,0x3f803f80,0x3f803f80,0x3f803f80,
  0x3f803f80,0x3f803f80,0x3f803f80,0x3f803f80,0x3f803f80,0x3f803f80,0x3f803f80,0x3f803f80,0x3f803f80,0x3f803f80,0x3f803f80,0x3f803f80,
  0x3f803f80,0x3f803f80,0x3f803f80,0x3f803f80,0x3f803f80,0x3f803f80,0x3f803f80,0x3f803f80,0x3f803f80,0x3f803f80,0x3f803f80,0x3f803f80,
  0x3f803f80,0x3f803f80,0x3f803f80,0x3f803f80,0x3f803f80,0x3f803f80,0x3f803f80,0x3f803f80,0x3f803f80,0x3f803f80,0x3f803f80,0x3f803f80,
  0x3f803f80,0x3f803f80,0x3f803f80,0x3f803f80,0x3f803f80,0x3f803f80,0x3f803f80,0x3f803f80,0x3f803f80,0x3f803f80,0x3f803f80,0x3f803f80,
  0x3f803f80,0x3f803f80,0x3f803f80,0x3f803f80,0x3f803f80,0x3f803f80,0x3f803f80,0x3f803f80,0x3f803f80,0x3f803f80,0x3f803f80,0x3f803f80,
  0x3f803f80,0x3f803f80,0x3f803f80,0x3f803f80,0x3f803f80,0x3f803f80,0x3f803f80,0x3f803f80,0x3f803f80,0x3f803f80,0x3f803f80,0x3f803f80,
  0x3f803f80,0x3f803f80,0x3f803f80,0x3f803f80,0x3f803f80,0x3f803f80,0x3f803f80,0x3f803f80,0x3f803f80,0x3f803f80,0x3f803f80,0x3f803f80,
  0x3f803f80,0x3f803f80,0x3f803f80,0x3f803f80,0x3f803f80,0x3f803f80,0x3f803f80,0x3f803f80,0x3f803f80,0x3f803f80,0x3f803f80,0x3f803f80,
  0x3f803f80,0x3f803f80,0x3f803f80,0x3f803f80,0x3f803f80,0x3f803f80,0x3f803f80,0x3f803f80,0x3f803f80,0x3f803f80,0x3f803f80,0x3f803f80,
  0x3f803f80,0x3f803f80,0x3f803f80,0x3f803f80,
};

__device__ __align__(128) float    g_part[16][8][2176];
__device__ __align__(128) float    g_kv[16][2176];
__device__ __align__(128) uint4    g_o[16 * 16 * 1024];
__device__ __align__(128) unsigned g_ocnt[2 * 16 * 32];
__device__ unsigned g_epoch[128];
#define GSTAMP(role, i) do {} while (0)
#define STAMP(role, i) do {} while (0)
#define PDUMP(role) do {} while (0)
#define PROF_SMEM 0

constexpr int STAGE_BYTES = 57344;
constexpr int OFF_H = 4 * 16384, OFF_VP = 9 * 16384, OFF_SPARE = 10 * 16384;
constexpr int OFF_XT = 172032, XT_STRIDE = 4112;
constexpr int OFF_BAR = 204928, OFF_EPOCH = OFF_BAR + 640, OFF_EX = OFF_BAR + 656, OFF_D = OFF_BAR + 672, OFF_SCALE = OFF_BAR + 704;
constexpr int OFF_F2F = 205824, OFF_F2I = 207872, OFF_F4 = 209920, OFF_ONES = 214016, OFF_KVB = 214016;
constexpr int OFF_STG = 219136, STG_STRIDE = 4352, SMEM_TOTAL = 232192 + PROF_SMEM;
enum { B_FULL1 = 0, B_EMPTY1 = 3, B_Q = 6, B_ODONE1 = 7, B_O1RDY = 8, B_H = 9, B_XRAW = 10, B_XT = 11, B_KV = 12, B_Y = 13,  B_AFREE = 15,
       B_STG = 18, B_ODONE = 24, B_XFREE = 25, B_FULL2 = 33, B_CONS2 = 49, B_SFREE = 14, B_PKRDY = 62, B_PKFREE = 64, B_H2 = 65, B_COUNT = 66 };
__host__ __device__ constexpr int bar_count(int i) {
  return i < B_EMPTY1 ? 1 : i < B_Q ? 4 : i == B_XT ? 4 : i == B_H ? 4 : i == B_SFREE ? 2 : i >= B_PKFREE ? 4 : i >= B_PKRDY ? 8 : i == B_KV ? 2 : i == B_Y ? 9
       : (i >= B_AFREE && i < B_STG) ? 16 : (i == B_ODONE || i == B_ODONE1) ? 8 : (i >= B_XFREE && i < B_FULL2) ? 4
       : i >= B_CONS2 ? 4 : (i >= B_FULL2 && i < B_FULL2 + 7) ? 2 : 1;
}
__host__ __device__ constexpr uint64_t bar_counts(int r) {
  uint64_t v = 0;
  for (int w = 0; w < 11; w++) v |= (uint64_t)(bar_count(1 + 11 * r + w) - 1) << (4 * w);
  return v;
}
constexpr uint64_t SLOT_A = 0x9645296452964594ull;
constexpr uint64_t SLOT_B = 0x7103871038710326ull;
constexpr uint32_t SW128 = 64 | (1u << 30);
constexpr int SPIN_LIMIT = 1 << 22;
#define PKV CU_TENSOR_MAP_L2_PROMOTION_L2_128B
#define BPRE B_KV
#define PFD 3
#define PD1 0
#define PD2 200
#define E1C 2
#define OSP 4
#define QPF 6
#define TSPLIT 1
#define OC0 2
#define OC1 2
#define BSPL 4
#define BPACE 250
#define NPOS 0
#define O1POS 1
#define HL1 4
#define OCH 3
#define O1D 1
#define QPOS 2
#define HOLD2 12
#define A0COL 0
#define KPOS 1
#define CWAIT 0
#define HSPL 32
#define BEARLY 3
#define BLATE B_KV
#define G2LA 0
#define G2W0 0
#define G2S 2
#define EPI2 1
#define X0U 1
#define S1E 0
#define D1 200
#define PREWPOS 0
#define TRICK 3
#define HSTART 1500
#define PACE 800
#define OC 1

__device__ __forceinline__ uint32_t smem_u32(const void* p) { return (uint32_t)__cvta_generic_to_shared(p); }
__device__ __forceinline__ void wg_fence() { asm volatile("wgmma.fence.sync.aligned;" ::: "memory"); }
__device__ __forceinline__ void wg_commit() { asm volatile("wgmma.commit_group.sync.aligned;" ::: "memory"); }
template <int N> __device__ __forceinline__ void wg_wait() { asm volatile("wgmma.wait_group.sync.aligned %0;" ::"n"(N) : "memory"); }
template <int N> __device__ __forceinline__ void keep(float (&d)[N]) {
#pragma unroll
  for (int i = 0; i < N; i++) asm volatile("" : "+f"(d[i])::"memory");
}
__device__ __forceinline__ uint64_t mkdesc(uint32_t addr, uint32_t lbo, uint32_t sbo, uint32_t swz) {
  uint32_t lo = ((addr & 0x3FFFF) >> 4) | ((lbo >> 4) << 16), hi = (sbo >> 4) | (swz << 30);
  return ((uint64_t)hi << 32) | lo;
}
__device__ __forceinline__ void mbar_init(uint32_t bar, int cnt) { asm volatile("mbarrier.init.shared::cta.b64 [%0], %1;" ::"r"(bar), "r"(cnt)); }
__device__ __forceinline__ void mbar_expect(uint32_t bar, int bytes) { asm volatile("mbarrier.arrive.expect_tx.shared::cta.b64 _, [%0], %1;" ::"r"(bar), "r"(bytes) : "memory"); }
__device__ __forceinline__ void mbar_arrive(uint32_t bar) { asm volatile("mbarrier.arrive.shared::cta.b64 _, [%0];" ::"r"(bar) : "memory"); }
__device__ __forceinline__ void mbar_arrive_cl(uint32_t bar, uint32_t cta) {
  asm volatile("{\n.reg .b32 r;\nmapa.shared::cluster.u32 r, %0, %1;\nmbarrier.arrive.shared::cluster.b64 _, [r];\n}\n" ::"r"(bar), "r"(cta) : "memory");
}
__device__ __forceinline__ void mbar_wait(uint32_t bar, uint32_t parity) {
  asm volatile("{\n.reg .pred p;\n.reg .u32 n;\nmov.u32 n, 0;\n"
               "W_%=:\nmbarrier.try_wait.parity.shared::cta.b64 p, [%0], %1;\n@p bra D_%=;\n"
               "add.u32 n, n, 1;\nsetp.lt.u32 p, n, %2;\n@p bra W_%=;\ntrap;\nD_%=:\n}\n" ::"r"(bar), "r"(parity), "n"(SPIN_LIMIT) : "memory");
}
__device__ __forceinline__ void fence_async() { asm volatile("fence.proxy.async.shared::cta;" ::: "memory"); }
__device__ __forceinline__ void bar_sync(int id) { asm volatile("bar.sync %0, 128;" ::"r"(id) : "memory"); }
__device__ __forceinline__ void tma2d(uint32_t dst, const CUtensorMap* m, int c0, int c1, uint32_t bar) {
  asm volatile("cp.async.bulk.tensor.2d.shared::cluster.global.mbarrier::complete_tx::bytes [%0], [%1, {%3, %4}], [%2];"
               ::"r"(dst), "l"(m), "r"(bar), "r"(c0), "r"(c1) : "memory");
}
__device__ __forceinline__ void tma2d_mc(uint32_t dst, const CUtensorMap* m, int c0, int c1, uint32_t bar) {
  asm volatile("cp.async.bulk.tensor.2d.shared::cluster.global.mbarrier::complete_tx::bytes.multicast::cluster [%0], [%1, {%3, %4}], [%2], %5;"
               ::"r"(dst), "l"(m), "r"(bar), "r"(c0), "r"(c1), "h"((uint16_t)3) : "memory");
}
__device__ __forceinline__ void tma3d(uint32_t dst, const CUtensorMap* m, int c0, int c1, int c2, uint32_t bar) {
  asm volatile("cp.async.bulk.tensor.3d.shared::cluster.global.mbarrier::complete_tx::bytes [%0], [%1, {%3, %4, %5}], [%2];"
               ::"r"(dst), "l"(m), "r"(bar), "r"(c0), "r"(c1), "r"(c2) : "memory");
}
__device__ __forceinline__ void tma4d(uint32_t dst, const CUtensorMap* m, int c0, int c1, int c2, int c3, uint32_t bar) {
  asm volatile("cp.async.bulk.tensor.4d.shared::cluster.global.mbarrier::complete_tx::bytes [%0], [%1, {%3, %4, %5, %6}], [%2];"
               ::"r"(dst), "l"(m), "r"(bar), "r"(c0), "r"(c1), "r"(c2), "r"(c3) : "memory");
}
__device__ __forceinline__ void bulk_ld(uint32_t dst, const void* src, int bytes, uint32_t bar) {
  asm volatile("cp.async.bulk.shared::cluster.global.mbarrier::complete_tx::bytes [%0], [%1], %2, [%3];" ::"r"(dst), "l"(src), "r"(bytes), "r"(bar) : "memory");
}
__device__ __forceinline__ void bulk_ld_mc(uint32_t dst, const void* src, int bytes, uint32_t bar) {
  asm volatile("cp.async.bulk.shared::cluster.global.mbarrier::complete_tx::bytes.multicast::cluster [%0], [%1], %2, [%3], %4;"
               ::"r"(dst), "l"(src), "r"(bytes), "r"(bar), "h"((uint16_t)3) : "memory");
}
__device__ __forceinline__ void tma2d_st(const CUtensorMap* m, uint32_t src, int c0, int c1) {
  asm volatile("cp.async.bulk.tensor.2d.global.shared::cta.bulk_group [%0, {%2, %3}], [%1];" ::"l"(m), "r"(src), "r"(c0), "r"(c1) : "memory");
}
__device__ __forceinline__ void pf_l2(const void* p, int bytes) { asm volatile("cp.async.bulk.prefetch.L2.global [%0], %1;" ::"l"(p), "r"(bytes) : "memory"); }
__device__ __forceinline__ void pf_t2d(const CUtensorMap* m, int c0, int c1) {
  asm volatile("cp.async.bulk.prefetch.tensor.2d.L2.global [%0, {%1, %2}];" ::"l"(m), "r"(c0), "r"(c1) : "memory");
}
__device__ __forceinline__ void pf_t3d(const CUtensorMap* m, int c0, int c1, int c2) {
  asm volatile("cp.async.bulk.prefetch.tensor.3d.L2.global [%0, {%1, %2, %3}];" ::"l"(m), "r"(c0), "r"(c1), "r"(c2) : "memory");
}
__device__ __forceinline__ void ldsm4(uint32_t (&r)[4], uint32_t a) {
  asm volatile("ldmatrix.sync.aligned.m8n8.x4.shared.b16 {%0,%1,%2,%3}, [%4];" : "=r"(r[0]), "=r"(r[1]), "=r"(r[2]), "=r"(r[3]) : "r"(a) : "memory");
}
__device__ __forceinline__ void ldsm4t(uint32_t (&r)[4], uint32_t a) {
  asm volatile("ldmatrix.sync.aligned.m8n8.x4.trans.shared.b16 {%0,%1,%2,%3}, [%4];" : "=r"(r[0]), "=r"(r[1]), "=r"(r[2]), "=r"(r[3]) : "r"(a) : "memory");
}
__device__ __forceinline__ void stsm4(uint32_t a, uint32_t r0, uint32_t r1, uint32_t r2, uint32_t r3) {
  asm volatile("stmatrix.sync.aligned.m8n8.x4.shared.b16 [%0], {%1,%2,%3,%4};" ::"r"(a), "r"(r0), "r"(r1), "r"(r2), "r"(r3) : "memory");
}
__device__ __forceinline__ uint32_t pk2(float lo, float hi) { uint32_t r; asm("cvt.rn.bf16x2.f32 %0, %1, %2;" : "=r"(r) : "f"(hi), "f"(lo)); return r; }
__device__ __forceinline__ uint32_t hmul(uint32_t a, uint32_t b) { uint32_t r; asm("mul.rn.bf16x2 %0, %1, %2;" : "=r"(r) : "r"(a), "r"(b)); return r; }
__device__ __forceinline__ uint32_t hadd(uint32_t a, uint32_t b) { uint32_t r; asm("add.rn.bf16x2 %0, %1, %2;" : "=r"(r) : "r"(a), "r"(b)); return r; }
__device__ __forceinline__ uint32_t hmax(uint32_t a, uint32_t b) { uint32_t r; asm("max.bf16x2 %0, %1, %2;" : "=r"(r) : "r"(a), "r"(b)); return r; }
__device__ __forceinline__ uint32_t hmin(uint32_t a, uint32_t b) { uint32_t r; asm("min.bf16x2 %0, %1, %2;" : "=r"(r) : "r"(a), "r"(b)); return r; }
__device__ __forceinline__ uint32_t hmaxabs(uint32_t a, uint32_t b) { uint32_t r; asm("max.xorsign.abs.bf16x2 %0, %1, %2;" : "=r"(r) : "r"(a), "r"(b)); return r; }
__device__ __forceinline__ float ex2(float x) { float r; asm("ex2.approx.ftz.f32 %0, %1;" : "=f"(r) : "f"(x)); return r; }
__device__ __forceinline__ float rcp_fast(float x) { float r; asm("rcp.approx.ftz.f32 %0, %1;" : "=f"(r) : "f"(x)); return r; }
__device__ __forceinline__ uint32_t phi2(float lo, float hi) {
  uint32_t t;
  asm("cvt.rn.relu.bf16x2.f32 %0, %1, %2;" : "=r"(t) : "f"(hi), "f"(lo));
  const uint32_t e = pk2(ex2(lo * 1.4426950408889634f), ex2(hi * 1.4426950408889634f));
  return hadd(hadd(t, hmin(e, 0x3F803F80u)), 0x35863586u);
}
__device__ __forceinline__ bool opaque_true() { uint32_t v; asm volatile("mov.u32 %0, %%nctaid.y;" : "=r"(v)); return v != 0; }
__device__ __forceinline__ int norm_exp(uint32_t (&v)[32], float f0) {
  uint32_t m[4] = {hmaxabs(__float_as_uint(f0) >> 16, v[0]), v[1], v[2], v[3]};
#pragma unroll
  for (int i = 4; i < 32; i++) m[i & 3] = hmaxabs(m[i & 3], v[i]);
  m[0] = hmaxabs(hmaxabs(m[0], m[1]), hmaxabs(m[2], m[3]));
  const int e = min(max((int)(__reduce_max_sync(~0u, max(m[0] & 0x7FFFu, (m[0] >> 16) & 0x7FFFu)) >> 7), 1), 253);
  if (e > 141) {
#pragma unroll
    for (int i = 0; i < 32; i++) v[i] = hmul(v[i], 0x07000700u);
  }
  return e;
}
template <int I0, int I1>
__device__ __forceinline__ void norm_cvt(uint32_t (&v)[32], float f0, int e) {
  const uint32_t sc = (e > 141 ? 255 - e : 142 - e) * 0x00800080u;
#pragma unroll
  for (int i = I0; i < I1; i++) {
    const uint32_t a = hmul(v[i], sc);
    v[i] = (a & 0x0FFF0FFFu) * 7 + a;
  }
  if (I0 == 0) v[0] = __byte_perm(v[0], __half_as_ushort(__float2half_rn(f0 * __uint_as_float((254 - e) << 23))), 0x3254);
}
__device__ __forceinline__ void poll_ge(const unsigned* p, unsigned target) {
#pragma unroll 1
  for (int n = 0; n < SPIN_LIMIT; n++) {
    unsigned v;
    asm volatile("ld.relaxed.gpu.global.u32 %0, [%1];" : "=r"(v) : "l"(p) : "memory");
    if (__all_sync(~0u, (int)(v - target) >= 0)) { asm volatile("fence.acquire.gpu;" ::: "memory"); return; }
  }
  __trap();
}

__device__ __forceinline__ bool elect_one() {
  uint32_t p;
  asm volatile("{\n.reg .pred p;\nelect.sync _|p, 0xffffffff;\nselp.u32 %0, 1, 0, p;\n}\n" : "=r"(p));
  return p;
}
__device__ __forceinline__ uint4 ld_nc4(const void* p) {
  uint4 v;
  asm volatile("ld.global.nc.L1::no_allocate.v4.u32 {%0,%1,%2,%3}, [%4];" : "=r"(v.x), "=r"(v.y), "=r"(v.z), "=r"(v.w) : "l"(p));
  return v;
}
__device__ __forceinline__ void st_cg4(void* p, uint4 v) {
  asm volatile("st.global.cg.v4.u32 [%0], {%1,%2,%3,%4};" ::"l"(p), "r"(v.x), "r"(v.y), "r"(v.z), "r"(v.w) : "memory");
}
__device__ __forceinline__ uint32_t mapa(uint32_t a, uint32_t cta) { uint32_t r; asm("mapa.shared::cluster.u32 %0, %1, %2;" : "=r"(r) : "r"(a), "r"(cta)); return r; }
__device__ __forceinline__ void st_async(uint32_t a, uint32_t v, uint32_t bar) {
  asm volatile("st.async.weak.shared::cluster.mbarrier::complete_tx::bytes.b32 [%0], %1, [%2];" ::"r"(a), "r"(v), "r"(bar) : "memory");
}
__device__ __forceinline__ void st_async4(uint32_t a, uint32_t x, uint32_t y, uint32_t z, uint32_t w, uint32_t bar) {
  asm volatile("st.async.weak.shared::cluster.mbarrier::complete_tx::bytes.v4.b32 [%0], {%1,%2,%3,%4}, [%5];" ::"r"(a), "r"(x), "r"(y), "r"(z), "r"(w), "r"(bar) : "memory");
}
__device__ __forceinline__ void tma3d_st(const CUtensorMap* m, uint32_t src, int c0, int c1, int c2) {
  asm volatile("cp.async.bulk.tensor.3d.global.shared::cta.bulk_group [%0, {%2, %3, %4}], [%1];" ::"l"(m), "r"(src), "r"(c0), "r"(c1), "r"(c2) : "memory");
}
__device__ __forceinline__ uint4 ld_rlx4(const void* p) {
  uint4 v;
  asm volatile("{\n.reg .b128 t;\n.reg .b64 a, b;\nld.relaxed.gpu.global.b128 t, [%4];\nmov.b128 {a, b}, t;\nmov.b64 {%0, %1}, a;\nmov.b64 {%2, %3}, b;\n}\n"
               : "=r"(v.x), "=r"(v.y), "=r"(v.z), "=r"(v.w) : "l"(p) : "memory");
  return v;
}
__device__ __forceinline__ void ld_stale4(uint4& v, const void* p, uint32_t tag) {
  asm volatile("{\n.reg .b128 t;\n.reg .b64 a, b;\n.reg .b32 x;\n.reg .pred p;\n"
               "lop3.b32 x, %0, %5, 1, 0x28;\nsetp.ne.u32 p, x, 0;\n"
               "mov.b64 a, {%0, %1};\nmov.b64 b, {%2, %3};\nmov.b128 t, {a, b};\n"
               "@p ld.relaxed.gpu.global.b128 t, [%4];\n"
               "mov.b128 {a, b}, t;\nmov.b64 {%0, %1}, a;\nmov.b64 {%2, %3}, b;\n}\n"
               : "+r"(v.x), "+r"(v.y), "+r"(v.z), "+r"(v.w) : "l"(p), "r"(tag) : "memory");
}
__device__ __forceinline__ void st_tag4(void* p, float a, float b, float c, float d, uint32_t tag) {
  asm volatile("{\n.reg .b128 t;\n.reg .b64 a, b;\nmov.b64 a, {%1, %2};\nmov.b64 b, {%3, %4};\nmov.b128 t, {a, b};\nst.relaxed.gpu.global.b128 [%0], t;\n}\n"
               ::"l"(p), "r"((__float_as_uint(a) & ~1u) | tag), "f"(b), "f"(c), "f"(d) : "memory");
}
__device__ __forceinline__ uint32_t stale8(const uint4 (&f)[8], uint32_t tag) {
  uint32_t r[4];
#pragma unroll
  for (int i = 0; i < 4; i++) asm("lop3.b32 %0, %1, %2, %3, 0x7E;" : "=r"(r[i]) : "r"(f[2 * i].x), "r"(f[2 * i + 1].x), "r"(tag));
  asm("lop3.b32 %0, %0, %1, %2, 0xFE;" : "+r"(r[0]) : "r"(r[1]), "r"(r[2]));
  return r[0] | r[3];
}

struct ConvC { uint32_t a1[2][4], wa[2], wb[2], sg; };
__device__ __forceinline__ uint64_t dsc(uint32_t lo, uint32_t hi) { return ((uint64_t)hi << 32) | lo; }
__device__ __forceinline__ uint32_t hfma(uint32_t a, uint32_t b, uint32_t c) { uint32_t r; asm("fma.rn.f16x2 %0, %1, %2, %3;" : "=r"(r) : "r"(a), "r"(b), "r"(c)); return r; }
__device__ __forceinline__ uint32_t hfnma(uint32_t a, uint32_t b, uint32_t c) { uint32_t r; asm("{.reg .b32 n; neg.f16x2 n, %1; fma.rn.f16x2 %0, n, %2, %3;}" : "=r"(r) : "r"(a), "r"(b), "r"(c)); return r; }
__device__ __forceinline__ uint32_t hmul16(uint32_t a, uint32_t b) { uint32_t r; asm("mul.rn.f16x2 %0, %1, %2;" : "=r"(r) : "r"(a), "r"(b)); return r; }
template <int N> __device__ __forceinline__ void keepu(uint32_t (&d)[N]) {
#pragma unroll
  for (int i = 0; i < N; i++) asm volatile("" : "+r"(d[i])::"memory");
}
__device__ __forceinline__ void conv_m1(const ConvC& K, uint32_t (&u)[16], uint32_t l) {
  wg_fence();
  wgmma_hrs_n64<1>(u, K.a1[0][0], K.a1[0][1], K.a1[0][2], K.a1[0][3], dsc(l, 32), 0);
  wgmma_hrs_n64<1>(u, K.a1[1][0], K.a1[1][1], K.a1[1][2], K.a1[1][3], dsc(l + 16, 32), 1);
  wg_commit();
}
__device__ __forceinline__ void conv_s2(const ConvC& K, uint32_t (&u)[16], uint32_t (&Z)[2][8], uint32_t dfl) {
  uint32_t fr[8], fi[8];
#pragma unroll
  for (int c = 0; c < 8; c++) {
    const uint32_t r = hfma(K.wa[c & 1], u[2 * c + 1], u[2 * c]);
    fi[c] = hfma(K.wb[c & 1], r, u[2 * c + 1]);
    fr[c] = hfma(K.wa[c & 1], fi[c], r);
  }
  wg_fence();
#pragma unroll
  for (int p = 0; p < 2; p++) {
    wgmma_hrs_n32<0>(Z[p], fr[4 * p], fr[4 * p + 2], fr[4 * p + 1], fr[4 * p + 3], dsc(dfl, 32), 0);
    wgmma_hrs_n32<0>(Z[p], fi[4 * p], fi[4 * p + 2], fi[4 * p + 1], fi[4 * p + 3], dsc(dfl + 16, 32), 1);
  }
  wg_commit();
}
__device__ __forceinline__ void conv_win(const ConvC& K, const uint32_t (&X)[2][8], uint32_t (&W)[2][8]) {
#pragma unroll
  for (int b = 0; b < 4; b++)
#pragma unroll
    for (int c = 0; c < 2; c++) {
      const uint32_t xr = X[b >> 1][2 * c + (b & 1)], xi = X[b >> 1][4 + 2 * c + (b & 1)];
      const int a = b ? b - 1 : 0;
      W[b >> 1][2 * c + (b & 1)] = b ? hfnma(K.sg, X[a >> 1][4 + 2 * c + (a & 1)], xr) : hmul16(xr, 0x3C003C00u);
      W[b >> 1][4 + 2 * c + (b & 1)] = b ? hfma(K.sg, X[a >> 1][2 * c + (a & 1)], xi) : hmul16(xi, 0x3C003C00u);
    }
}
template <int p>
__device__ __forceinline__ void conv_pw(uint32_t (&X)[2][8], uint32_t (&H)[2][8], uint32_t (&V)[8], uint32_t dil) {
  uint32_t pr[2][2], pi[2][2];
#pragma unroll
  for (int jj = 0; jj < 2; jj++)
#pragma unroll
    for (int c = 0; c < 2; c++) {
      const int j = 2 * p + jj;
      uint32_t sr = 0, si = 0;
#pragma unroll
      for (int a = 0; a <= j; a++) {
        const int b = j - a;
        const uint32_t hr = H[a >> 1][2 * c + (a & 1)], hi = H[a >> 1][4 + 2 * c + (a & 1)];
        const uint32_t xr = X[b >> 1][2 * c + (b & 1)], xi = X[b >> 1][4 + 2 * c + (b & 1)];
        sr = a == 0 ? hmul16(hr, xr) : hfma(hr, xr, sr);
        si = a == 0 ? hmul16(hr, xi) : hfma(hr, xi, si);
        sr = hfnma(hi, xi, sr);
        si = hfma(hi, xr, si);
      }
      pr[jj][c] = sr; pi[jj][c] = si;
    }
  wg_fence();
  wgmma_hrs_n32<0>(V, pr[0][0], pr[1][0], pr[0][1], pr[1][1], dsc(dil, 32), 0);
  wgmma_hrs_n32<0>(V, pi[0][0], pi[1][0], pi[0][1], pi[1][1], dsc(dil + 16, 32), 1);
  wg_commit();
}
template <int p>
__device__ __forceinline__ void conv_it(const ConvC& K, uint32_t (&V)[8], uint32_t vst) {
#pragma unroll
  for (int jj = 0; jj < 2; jj++) {
    uint32_t wr[2], wi[2];
#pragma unroll
    for (int c = 0; c < 2; c++) {
      const uint32_t r = hfnma(K.wa[c], V[4 + 2 * c + jj], V[2 * c + jj]);
      wi[c] = hfnma(K.wb[c], r, V[4 + 2 * c + jj]);
      wr[c] = hfnma(K.wa[c], wi[c], r);
    }
    stsm4(vst + (2 * p + jj) * 2048, wr[0], wr[1], wi[0], wi[1]);
  }
}
__device__ __forceinline__ void conv_m4(uint32_t (&y)[8], uint32_t (&a)[4][4], uint32_t d4l) {
  wg_fence();
  wgmma_hrs_n32<0>(y, a[0][0], a[0][1], a[0][2], a[0][3], dsc(d4l, 64), 0);
#pragma unroll
  for (int s = 1; s < 4; s++) wgmma_hrs_n32<0>(y, a[s][0], a[s][1], a[s][2], a[s][3], dsc(d4l + s * 16, 64), 1);
  wg_commit();
}

struct Params {
  CUtensorMap tmX, tmW, tmWo, tmWo1, tmK, tmV, tmQ, tmOA, tmOB;
  const __nv_bfloat16 *shift_k, *h, *D, *x, *w, *wo, *q;
  float *part, *kv;
  uint4* o;
  unsigned *ocnt, *epoch;
  const uint32_t *thr, *img;
};

__global__ void __cluster_dims__(2, 1, 1) __launch_bounds__(384, 1) fused_kernel(const __grid_constant__ Params P) {
  extern __shared__ __align__(1024) uint8_t smem[];
  const uint32_t sb = __shfl_sync(~0u, smem_u32(smem), 0);
  const uint32_t bars = sb + OFF_BAR;
  const int tid = threadIdx.x, lane = tid & 31;
  const int warp = __shfl_sync(~0u, tid >> 5, 0);
  const int rank = blockIdx.x & 1, cl = blockIdx.x >> 1;
  const int mb = cl < 4 ? 4 + cl : cl < 36 ? (cl - 4) >> 3 : 4 + (cl - 36) / 7;
  const int hb = (cl - 36) % 7;
  const int hq = cl < 4 ? A0COL : cl < 36 ? (cl - 4) & 7 : hb + (hb >= A0COL);
  const int hp = 2 * hq + rank;
  const int rb = 2 * mb + (hq >> 2), cb = hq & 3;
#define BAR(i) (bars + 8 * (i))

  if (tid == 0) { STAMP(0, 0); GSTAMP(0, 30); }
  if (warp == 8) {
    if (elect_one()) {
      mbar_init(BAR(B_FULL1), 1);
      asm volatile("fence.mbarrier_init.release.cluster;" ::: "memory");
      mbar_expect(BAR(B_FULL1), STAGE_BYTES);
      if (X0U == 1) { tma2d(sb, &P.tmX, 0, mb * 256, BAR(B_FULL1)); tma2d(sb + 16384, &P.tmX, 0, mb * 256 + 128, BAR(B_FULL1)); }
      tma3d(sb + 32768, &P.tmW, hp * 64, 0, 0, BAR(B_FULL1));
      if (X0U == 2) { tma2d(sb, &P.tmX, 0, mb * 256, BAR(B_FULL1)); tma2d(sb + 16384, &P.tmX, 0, mb * 256 + 128, BAR(B_FULL1)); }
    }
    if (lane == 0) STAMP(3, 21);
  } else if (lane == 0) {
    const int wi = warp - (warp > 8);
#pragma unroll
    for (int r = 0; r < 6; r++)
      if (r < 5 || wi < B_COUNT - 56) mbar_init(BAR(1 + 11 * r + wi), ((uint32_t)(bar_counts(r) >> (4 * wi)) & 15) + 1);
    asm volatile("fence.mbarrier_init.release.cluster;" ::: "memory");
  }
  if (tid == 0) STAMP(2, 6);
  asm volatile("barrier.cluster.arrive.relaxed.aligned;\nbarrier.cluster.wait.aligned;" ::: "memory");
  if (warp == 8 && elect_one()) {
    if (!X0U) tma2d_mc(sb + rank * 16384, &P.tmX, 0, mb * 256 + rank * 128, BAR(B_FULL1));
    if (S1E) {
      mbar_expect(BAR(B_FULL1 + 1), STAGE_BYTES);
      tma2d_mc(sb + STAGE_BYTES + rank * 16384, &P.tmX, 64, mb * 256 + rank * 128, BAR(B_FULL1 + 1));
      tma3d(sb + STAGE_BYTES + 32768, &P.tmW, hp * 64, 64, 0, BAR(B_FULL1 + 1));
    }
  }
  if (tid == 256) STAMP(2, 7);

  if (warp < 8) {
    asm volatile("setmaxnreg.inc.sync.aligned.u32 224;");
    const int wg = warp >> 2, w = warp & 3, g = lane >> 2, q = lane & 3, t = tid & 127;
    const bool elect = (t == 0);
    const uint32_t s16 = (sb & 0x3FFFF) >> 4;
    uint32_t pq[2][16];
    ConvC K;
    {
      float acc[2][96];
      int st = 0, ph = 0;
#pragma unroll 1
      for (int kb = 0; kb < 14; kb++) {
        mbar_wait(BAR(B_FULL1 + st), ph);
        if (kb == 0 && elect) { STAMP(wg, 1); GSTAMP(wg, 26); }
        if (kb == 8 && elect) { STAMP(wg, 16); GSTAMP(wg, 25); }
        if (G2S == 3 && tid == 0) STAMP(2, 8 + kb);
        const uint32_t da = s16 + st * (STAGE_BYTES >> 4) + wg * 1024 + (1 << 16);
        const uint32_t db = s16 + st * (STAGE_BYTES >> 4) + 2048 + (512 << 16);
        wg_fence();
#pragma unroll
        for (int ks = 0; ks < 4; ks++) {
          wgmma_ss_n192<0, 1>(acc[0], dsc(da + ks * 2, SW128), dsc(db + ks * 128, SW128), (kb | ks) != 0);
          wgmma_ss_n192<0, 1>(acc[1], dsc(da + 512 + ks * 2, SW128), dsc(db + ks * 128, SW128), (kb | ks) != 0);
        }
        wg_commit();
        wg_wait<1>();
        if (kb > 0 && t < 2) mbar_arrive_cl(BAR(B_EMPTY1 + (st == 0 ? 2 : st - 1)), t);
        if (++st == 3) { st = 0; ph ^= 1; }
      }
#define TAIL_MMA(mt, stage) do { wg_fence(); _Pragma("unroll") for (int ks = 0; ks < 4; ks++) \
        wgmma_ss_n192<0, 1>(acc[mt], dsc(s16 + (stage) * (STAGE_BYTES >> 4) + wg * 1024 + (mt) * 512 + (1 << 16) + ks * 2, SW128), \
                            dsc(s16 + (stage) * (STAGE_BYTES >> 4) + 2048 + (512 << 16) + ks * 128, SW128), 1); wg_commit(); } while (0)
      mbar_wait(BAR(B_FULL1 + 2), 0);
      TAIL_MMA(0, 2);
      wg_wait<1>();
      if (elect) mbar_arrive(BAR(B_SFREE));
      mbar_wait(BAR(B_FULL1 + 0), 1);
      TAIL_MMA(0, 0);
      TAIL_MMA(1, 2);
      const uint32_t lrow = sb + wg * 16384 + (16 * w + 8 * ((lane >> 3) & 1) + (lane & 7)) * 128 + (((lane >> 4) ^ (lane & 7)) << 4);
#define E1K(mt, i) do { if (opaque_true()) { _Pragma("unroll") for (int j = (i); j < (i) + 2; j++) { \
          const float* a = &acc[mt][32 + 8 * j]; const float* b = a + 32; const uint32_t o = (lrow ^ (j * 32)) + (mt) * 8192; \
          stsm4(o + 2 * STAGE_BYTES, pk2(b[0], b[1]), pk2(b[2], b[3]), pk2(b[4], b[5]), pk2(b[6], b[7])); \
          stsm4(o, phi2(a[0], a[1]), phi2(a[2], a[3]), phi2(a[4], a[5]), phi2(a[6], a[7])); } } } while (0)
#define E1Q(mt) do { if (opaque_true()) { _Pragma("unroll") for (int i = 0; i < 16; i++) pq[mt][i] = phi2(acc[mt][2 * i], acc[mt][2 * i + 1]); } } while (0)
#define PK_READY(mt) do { fence_async(); __syncwarp(); if (lane == 0) mbar_arrive(BAR(B_PKRDY + (mt))); } while (0)
      wg_wait<1>();
      keep(acc[0]);
      if (elect) STAMP(wg, 18);
      E1K(0, 0);
      TAIL_MMA(1, 0);
      E1K(0, 2);
      if (elect) STAMP(wg, 19);
      PK_READY(0);
      wg_wait<0>();
      keep(acc[1]);
      asm volatile("setmaxnreg.dec.sync.aligned.u32 200;");
      if (elect) { STAMP(wg, 2); GSTAMP(wg, 27); }
      E1K(1, 0);
      E1K(1, 2);
      PK_READY(1);
      if (elect) STAMP(wg, 3);
      {
        const uint4* ct = (const uint4*)P.thr + t;
#pragma unroll
        for (int s = 0; s < 2; s++) { const uint4 u = ld_nc4(ct + s * 128); K.a1[s][0] = u.x; K.a1[s][1] = u.y; K.a1[s][2] = u.z; K.a1[s][3] = u.w; }
        const uint4 u = ld_nc4(ct + 2 * 128);
        K.wa[0] = u.x; K.wa[1] = u.y; K.wb[0] = u.z; K.wb[1] = u.w;
        K.sg = (lane & 4) ? 0xBC00BC00u : 0x3C003C00u;
      }
      if (CWAIT) mbar_wait(BAR(B_PKFREE), 0);
      if (elect) STAMP(wg, 4);
      E1Q(0);
      E1Q(1);
    }
    if (elect) STAMP(wg, 17);
    mbar_wait(BAR(B_H), 0);
    mbar_wait(BAR(B_PKRDY + 1), 0);
    if (elect) STAMP(wg, 5);
    {
      const uint32_t dfl = s16 + (OFF_F2F >> 4) + (8 << 16), dil = s16 + (OFF_F2I >> 4) + (8 << 16), d4l = s16 + (OFF_F4 >> 4) + (8 << 16);
      const uint32_t xl = s16 + (OFF_XT >> 4) + 4 * wg * (XT_STRIDE >> 4) + (8 << 16);
      const uint32_t hl = s16 + (OFF_H >> 4) + wg * 512 + (8 << 16);
      uint32_t vst = sb + wg * 8192 + w * 512 + lane * 16, vld = sb + wg * 8192 + w * 2048 + lane * 16;
      uint32_t ya = mapa(sb + OFF_XT + 4 * wg * XT_STRIDE + (2 * rank + (w & 1)) * 1024 + lane * 16, w >> 1);
      const uint32_t ybar = mapa(BAR(B_Y), w >> 1);
      asm volatile("" : "+r"(vst), "+r"(vld), "+r"(ya));
      uint32_t ux[16], uh[16], W[2][8], V0[8], V1[8], y[8], a[4][4];
      uint4 ov[4];
      uint4* const ot = P.o + ((2 * mb + wg) * 16 + hq) * 1024 + (16 * w + g) * 8 + ((4 * rank + q) ^ g);
#define YOUT(i) do { if ((w >> 1) == rank) { \
          asm volatile("st.shared.v4.b32 [%0], {%1,%2,%3,%4};" ::"r"(ya + (i) * XT_STRIDE), "r"(y[0]), "r"(y[2]), "r"(y[4]), "r"(y[6]) : "memory"); \
          asm volatile("st.shared.v4.b32 [%0], {%1,%2,%3,%4};" ::"r"(ya + (i) * XT_STRIDE + 512), "r"(y[1]), "r"(y[3]), "r"(y[5]), "r"(y[7]) : "memory"); \
        } else { \
          mbar_wait(BAR(B_XFREE + 4 * wg + (i)), 0); \
          st_async4(ya + (i) * XT_STRIDE, y[0], y[2], y[4], y[6], ybar); \
          st_async4(ya + (i) * XT_STRIDE + 512, y[1], y[3], y[5], y[7], ybar); } } while (0)
      auto ocalc = [&](const int hh) {
        if (hh == 0) {
          if (elect) STAMP(wg, 8);
          mbar_wait(BAR(B_KV), 0);
          if (elect) STAMP(wg, 9);
        }
        float oa[2][20];
        wg_fence();
#pragma unroll
        for (int m = 0; m < 4; m++) {
          const uint32_t* p = &pq[m & 1][8 * hh + 4 * (m >> 1)];
          wgmma_rs_n40<1>(oa[m & 1], p[0], p[1], p[2], p[3], dsc(s16 + (OFF_KVB >> 4) + hh * 160 + (m >> 1) * 16 + (8 << 16), 32), m >> 1);
        }
        wg_commit();
        wg_wait<0>();
#pragma unroll
        for (int mt = 0; mt < 2; mt++) {
          float (&o)[20] = oa[mt];
          keep(o);
          const uint32_t den = hadd(pk2(o[16], o[18]), 0x35863586u);
#pragma unroll
          for (int r = 0; r < 2; r++) {
            const float ri = rcp_fast(__uint_as_float(r ? (den & 0xFFFF0000u) : (den << 16)));
            uint4 u;
            u.x = pk2(o[2 * r] * ri, o[2 * r + 1] * ri);
            u.y = pk2(o[4 + 2 * r] * ri, o[5 + 2 * r] * ri);
            u.z = pk2(o[8 + 2 * r] * ri, o[9 + 2 * r] * ri);
            u.w = pk2(o[12 + 2 * r] * ri, o[13 + 2 * r] * ri);
            if (hh == 0 || !TRICK) st_cg4(ot + hh * 8 * 1024 + (64 * mt + 8 * r) * 8, u); else ov[2 * mt + r] = u;
          }
        }
        if (hh == 1 && TRICK) return;
        __syncwarp();
        if (lane == 0) mbar_arrive(BAR(hh ? B_ODONE1 : B_ODONE));
        if (hh == 0 && elect) STAMP(wg, 10);
      };
      auto trickle = [&](const int qs) {
        const int m = qs - 2 * (OCH + O1D) - (TRICK - 1);
        if (TRICK && m >= 0 && m < 4) {
          st_cg4(ot + 8 * 1024 + (64 * (m >> 1) + 8 * (m & 1)) * 8, ov[m]);
          if (m == 3) { __syncwarp(); if (lane == 0) mbar_arrive(BAR(B_ODONE1)); }
        }
      };
      uint32_t X[4][2][8], H[4][2][8];
      conv_m1(K, ux, xl);
      conv_m1(K, uh, hl);
      wg_wait<1>(); keepu(ux);
      if (lane == 0) mbar_arrive_cl(BAR(B_XFREE + 4 * wg), rank ^ 1);
      conv_s2(K, ux, X[0], dfl);
      wg_wait<1>(); keepu(uh);
      conv_s2(K, uh, H[0], dfl);
#pragma unroll
      for (int i = 0; i < 4; i++) {
        const bool nx = i < 3;
        const int n = nx ? i + 1 : i;
        const uint32_t vo = (i & 1) ? OFF_H + (i >> 1) * 16384 : OFF_VP;
        if (2 * i == OCH) ocalc(0);
        if (2 * i == OCH + O1D) ocalc(1);
        if (nx) {
          if (n == 2) mbar_wait(BAR(B_H2), 0);
          conv_m1(K, ux, xl + n * (XT_STRIDE >> 4));
          conv_m1(K, uh, hl + (n >> 1) * 1024 + (n & 1) * 256);
        }
        if (2 * i != OCH && 2 * i != OCH + O1D) { if (nx) { if (i > 0) wg_wait<3>(); else wg_wait<2>(); } else wg_wait<1>(); }
        keepu(X[i][0]); keepu(X[i][1]); keepu(H[i][0]); keepu(H[i][1]);
        conv_win(K, X[i], W);
        trickle(4 * i);
        conv_pw<0>(W, H[i], V0, dil);
        conv_pw<1>(W, H[i], V1, dil);
        trickle(4 * i + 1);
        wg_wait<2>();
        if (i > 0) { keepu(y); YOUT(i - 1); }
        if (2 * i + 1 == OCH) ocalc(0);
        if (2 * i + 1 == OCH + O1D) ocalc(1);
        if (nx) {
          keepu(ux); keepu(uh);
          if (lane == 0) mbar_arrive_cl(BAR(B_XFREE + 4 * wg + n), rank ^ 1);
          conv_s2(K, ux, X[n], dfl);
          wg_wait<1>();
        } else wg_wait<0>();
        keepu(V0); keepu(V1);
        trickle(4 * i + 2);
        conv_it<0>(K, V0, vst + vo);
        conv_it<1>(K, V1, vst + vo);
        bar_sync(1 + wg);
#pragma unroll
        for (int s = 0; s < 4; s++) ldsm4t(a[s], vld + vo + s * 512);
        if (nx) conv_s2(K, uh, H[n], dfl);
        conv_m4(y, a, d4l);
        trickle(4 * i + 3);
        if (i > 0 && lane < 2) mbar_arrive_cl(BAR(B_AFREE + i - 1), lane);
        if (elect && i < 3) STAMP(wg, i < 2 ? 6 + i : 9 + i);
      }
      wg_wait<0>(); keepu(y);
      YOUT(3);
      if (OCH + O1D >= 8) ocalc(1);
      __syncwarp();
      if (lane == 0) mbar_arrive(BAR(B_Y));
      if (elect) STAMP(wg, 12);
    }
    {
      float acc[64];
#define G2_MMA(da, db, first) do { wg_fence(); _Pragma("unroll") for (int ks = 0; ks < 4; ks++) \
        wgmma_ss_n128<0, 1>(acc, dsc((da) + ks * 2, SW128), dsc((db) + ks * 128, SW128), ks || !(first)); wg_commit(); } while (0)
      const uint32_t a0 = s16 + wg * 512 + (1 << 16), b0 = s16 + (512 << 16);
      uint64_t ta = SLOT_A, tb = SLOT_B;
      uint32_t da = a0 + (SLOT_A & 15) * 1024, db = b0 + (SLOT_B & 15) * 1024, fb = BAR(B_FULL2);
      uint32_t cons = mapa(BAR(B_CONS2 - 1), t & 1);
      const bool rel = __shfl_sync(~0u, t, lane) < 2;
#pragma unroll 1
      for (int kb = 0; kb < HOLD2; kb++) {
        if (G2S == 0 && tid == 128) STAMP(2, 8 + kb);
        mbar_wait(fb, 0);
        if (G2S == 1 && tid == 128) STAMP(2, 8 + kb);
        if (kb == 0 && elect) { STAMP(wg, 13); GSTAMP(wg, 28); }
        G2_MMA(da, db, kb == 0);
        ta >>= 4; tb >>= 4;
        da = a0 + ((uint32_t)ta & 15) * 1024; db = b0 + ((uint32_t)tb & 15) * 1024; fb += 8;
        asm volatile("" : "+r"(da), "+r"(db));
        wg_wait<1>();
        if (kb > 0 && kb < 12 && rel) asm volatile("mbarrier.arrive.shared::cluster.b64 _, [%0];" ::"r"(cons) : "memory");
        cons += 8;
      }
      if (HOLD2 == 11) { wg_wait<0>(); if (rel) asm volatile("mbarrier.arrive.shared::cluster.b64 _, [%0];" ::"r"(cons) : "memory"); }
#pragma unroll
      for (int kb = HOLD2; kb < 16; kb++) {
        if (wg == 1) mbar_wait(BAR(B_FULL2 + kb), 0);
        else if (kb == HOLD2) asm volatile("bar.sync 3, 256;" ::: "memory");
        G2_MMA(a0 + ((SLOT_A >> (4 * kb)) & 15) * 1024, b0 + ((SLOT_B >> (4 * kb)) & 15) * 1024, false);
      }
      if (wg == 1) asm volatile("bar.arrive 3, 256;" ::: "memory");
      const uint32_t stg = sb + wg * 8192 + w * 2048, so0 = ((SLOT_A >> 56) & 15) * 16384, so1 = ((SLOT_A >> 60) & 15) * 16384;
      const uint32_t lrow = stg + (8 * ((lane >> 3) & 1) + (lane & 7)) * 128 + (((lane >> 4) ^ (lane & 7)) << 4);
      const int col = 1024 + 256 * cb + 128 * rank, row = 128 * rb + 64 * wg + 16 * w;
      wg_wait<0>();
      keep(acc);
      if (elect) { STAMP(wg, 14); GSTAMP(wg, 29); }
#pragma unroll
      for (int cp = 0; cp < 8; cp++) {
        const float* a = &acc[8 * cp];
        stsm4((lrow ^ ((cp & 3) * 32)) + (cp >> 2 ? so1 : so0), pk2(a[0], a[1]), pk2(a[2], a[3]), pk2(a[4], a[5]), pk2(a[6], a[7]));
        if (cp == 7 || (EPI2 && cp == 3)) {
          fence_async();
          __syncwarp();
          if (elect_one()) {
            if (cp == 3 || !EPI2) tma2d_st(&P.tmOB, stg + so0, col, row);
            if (cp == 7) tma2d_st(&P.tmOB, stg + so1, col + 64, row);
          }
        }
      }
      asm volatile("cp.async.bulk.commit_group;\ncp.async.bulk.wait_group.read 0;" ::: "memory");
      if (elect) {
        STAMP(wg, 15); GSTAMP(wg, 31); PDUMP(wg); if (wg == 0) PDUMP(2);
      }
    }
  } else {
    asm volatile("setmaxnreg.dec.sync.aligned.u32 56;");
    const int hw = warp - 9, g = lane >> 2, q = lane & 3;
#define sbar (bars + 8 * (B_STG - 18) + 16 * warp)
    if (warp == 8) {
      if (D1) __nanosleep(D1);
      int st = 1 + S1E, pp = 1;
      const uint8_t* pfx = (const uint8_t*)P.x + (mb * 256 + hp * 16 + (lane & 15)) * 2048;
      const uint8_t* pfw = (const uint8_t*)P.w + (mb * 8 + (lane & 7)) * 6144 + (lane >> 3) * 2048 + hp * 128;
#pragma unroll 1
      for (int kb = 1 + S1E; kb < 16; kb++) {
        if (kb >= 3) mbar_wait(BAR(B_EMPTY1 + st), pp);
        const uint32_t sa = sb + st * STAGE_BYTES;
        if (elect_one()) {
          mbar_expect(BAR(B_FULL1 + st), STAGE_BYTES);
          tma2d_mc(sa + rank * 16384, &P.tmX, kb * 64, mb * 256 + rank * 128, BAR(B_FULL1 + st));
          tma3d(sa + 32768, &P.tmW, hp * 64, kb * 64, 0, BAR(B_FULL1 + st));
        }
        if (kb == 1 && lane == 0) STAMP(2, 24);
        if (PFD && kb >= 2) {
#pragma unroll 1
          for (int j = kb == 2 ? 3 : kb + PFD; j <= kb + PFD && j < 16; j++) {
            if (lane < 16) asm volatile("prefetch.global.L2 [%0];" ::"l"(pfx + j * 128));
            if (lane < 24) asm volatile("prefetch.global.L2 [%0];" ::"l"(pfw + j * (64 * 6144)));
          }
          if (kb >= QPF && kb < QPF + 8) asm volatile("prefetch.global.L2 [%0];" ::"l"((const uint8_t*)P.q + (blockIdx.x * 256 + (kb - QPF) * 32 + lane) * 128));
          if (kb >= 4)
            asm volatile("prefetch.global.L2 [%0];" ::"l"(kb < 12 ? (const uint8_t*)P.h + (blockIdx.x * 256 + (kb - 4) * 32 + lane) * 128
                                                                  : (const uint8_t*)P.wo + (blockIdx.x * 128 + (kb - 12) * 32 + lane) * 128));
        }
        if (++st == 3) { st = 0; pp ^= 1; }
      }
      if (lane == 0) STAMP(2, 1);
    } else {
      {
        const uint32_t clk0 = __shfl_sync(~0u, (uint32_t)clock(), 0), stg = sb + OFF_STG + hw * STG_STRIDE;
        const unsigned epoch = __shfl_sync(~0u, P.epoch[blockIdx.x], 0);
        const uint32_t tag = ~epoch & 1;
        uint32_t tap[2][4];
#pragma unroll
        for (int cg = 0; cg < 2; cg++) {
          const uint2 u = __ldg((const uint2*)(P.shift_k + (16 * cl + 8 * cg + g) * 4));
          tap[cg][0] = __byte_perm(u.x, 0, 0x1010); tap[cg][1] = __byte_perm(u.x, 0, 0x3232);
          tap[cg][2] = __byte_perm(u.y, 0, 0x1010); tap[cg][3] = __byte_perm(u.y, 0, 0x3232);
        }
        if (hw == 0 && lane < 8) *(float*)(smem + OFF_D + 4 * lane) = __bfloat162float(P.D[blockIdx.x * 8 + lane]);
        if (hw == 1) asm volatile("prefetch.global.L2 [%0];" ::"l"(P.thr + (lane + 32 * (blockIdx.x & 1)) * 32));
        if (hw == 0 && elect_one()) {
          *(volatile unsigned*)(smem + OFF_EPOCH) = epoch;
          mbar_expect(BAR(B_XRAW), 16384);
          mbar_expect(BAR(B_Y), 16384 + 64);
        }
        for (int i = hw * 32 + lane; i < 528; i += 96) st_tag4(P.part + (hp * 8 + mb) * 2176 + 4 * i, 0.f, 0.f, 0.f, 0.f, tag ^ 1);
        if (hw < 2 || lane < 2) st_tag4(P.kv + hp * 2176 + (4 * (hw < 2 ? 64 * mb + 32 * hw + lane : 512 + 2 * mb + lane)), 0.f, 0.f, 0.f, 0.f, tag ^ 1);
        if (lane == 0) STAMP(3, hw);
        const uint32_t xo = sb + OFF_XT + g * XT_STRIDE + rank * 2048 + q * 4;
        const int krow = 8 + (lane & 7) - (lane >> 3);
        const uint32_t ka = stg + krow * 32 + ((krow & 4) << 2), va = stg + 2304 + lane * 32 + ((lane & 4) << 2);
        int ph = 0, b = 0;
#pragma unroll 1
        for (int ci = hw - 3; ci < 16; ci += 3) {
          const uint32_t bo = b ? OFF_F2F - OFF_STG : 0, bn = b ? 0 : OFF_F2F - OFF_STG;
          if (ci + 3 < 16) {
            while (__any_sync(~0u, (uint32_t)clock() - clk0 < HSTART + (ci + 3) * PACE)) __nanosleep(64);
            if (elect_one()) {
              mbar_expect(sbar + 8 * (b ^ 1), 2304 + 2048);
              tma2d(stg + bn, &P.tmK, 16 * cl, 1024 * rank + 64 * (ci + 3) - 8, sbar + 8 * (b ^ 1));
              tma2d(stg + bn + 2304, &P.tmV, 16 * cl, 1024 * rank + 64 * (ci + 3), sbar + 8 * (b ^ 1));
            }
          }
          if (ci >= 0) {
            mbar_wait(sbar + 8 * b, (ph >> b) & 1);
            ph ^= 1 << b;
#pragma unroll 1
            for (int grp = 0; grp < 2; grp++) {
#pragma unroll
              for (int cg = 0; cg < 2; cg++) {
                const uint32_t dst = mapa(xo + (ci >> 3) * 1024 + ((ci & 7) * 4 + 2 * grp) * 16, cg), xbar = mapa(BAR(B_XRAW), cg);
                uint32_t vv[4], kk[4][4];
                ldsm4t(vv, (va ^ (cg * 16)) + bo + grp * 1024);
#pragma unroll
                for (int rg = 0; rg < 4; rg++) ldsm4t(kk[rg], (ka ^ (cg * 16)) + bo + grp * 1024 + rg * 256);
#pragma unroll
                for (int rg = 0; rg < 4; rg++)
                  vv[rg] = hmul(hadd(hadd(hadd(hmul(kk[rg][3], tap[cg][3]), hmul(kk[rg][2], tap[cg][2])), hmul(kk[rg][1], tap[cg][1])), hmul(kk[rg][0], tap[cg][0])), vv[rg]);
                if (cg == rank) {
#pragma unroll
                  for (int rg = 0; rg < 4; rg++) asm volatile("st.shared.b32 [%0], %1;" ::"r"(dst + (rg & 1) * 512 + (rg >> 1) * 16), "r"(vv[rg]) : "memory");
                } else {
#pragma unroll
                  for (int rg = 0; rg < 4; rg++) st_async(dst + (rg & 1) * 512 + (rg >> 1) * 16, vv[rg], xbar);
                }
              }
            }
          }
          b ^= 1;
        }
      }
      if (lane == 0) STAMP(3, 3 + hw);
      asm volatile("bar.sync 4, 96;" ::: "memory");
      if (hw == 0 && elect_one()) { mbar_expect(BAR(B_XT), 10240); bulk_ld(sb + OFF_F2F, P.img, 10240, BAR(B_XT)); }
      mbar_wait(BAR(B_XRAW), 0);
    }
#pragma unroll 1
    for (int n = hw < 0 ? 3 : 0; n < 4; n++) {
      const bool isH = n >= 3;
      const int c = isH ? (warp & 1) + 2 * (warp & 2) : hw + 3 * n;
      if (c < 8) {
        int ln;
        asm volatile("mov.u32 %0, %%laneid;" : "=r"(ln));
        uint8_t* dst = smem + (isH ? OFF_H + (c & 2) * 8192 + (c >> 2) * 8192 + (c & 1) * 4096 : OFF_XT + c * XT_STRIDE) + ((ln >> 4) * 512 + (ln & 15) * 16);
        const uint8_t* src0 = isH ? (const uint8_t*)P.h + (blockIdx.x * 8 + c) * 4096 + ((ln & 15) * 32 + (ln & 16)) : dst;
        const uint8_t* src1 = src0 + (isH ? 512 : 256);
        uint32_t v[32];
#pragma unroll
        for (int i = 0; i < 8; i++) {
          const uint4 u = *(const uint4*)(((i & 1) ? src1 : src0) + (i >> 1) * 1024);
          v[4 * i] = u.x; v[4 * i + 1] = u.y; v[4 * i + 2] = u.z; v[4 * i + 3] = u.w;
        }
        if (isH) mbar_wait(BAR(B_XT), 0);
        const float f0 = __uint_as_float(v[0] << 16) + ((isH && ln == 0) ? *(const float*)(smem + OFF_D + 4 * c) : 0.f);
        const int e = norm_exp(v, f0);
        norm_cvt<0, 32>(v, f0, e);
        if (isH) {
          if (ln < 2) st_async(mapa(sb + OFF_SCALE + (8 * rank + c) * 4, ln), min(max(e + smem[OFF_EX + c] - 124, 1), 254) << 23, mapa(BAR(B_Y), ln));
          mbar_wait(BAR(B_SFREE), 0);
        } else if (ln == 0) smem[OFF_EX + c] = e;
#pragma unroll
        for (int i = 0; i < 8; i++)
          *(uint4*)(dst + (i >> 1) * 1024 + (i & 1) * 256) = make_uint4(v[4 * i], v[4 * i + 1], v[4 * i + 2], v[4 * i + 3]);
        if (n < 2 && elect_one()) {
          if (n == 0) mbar_expect(sbar, 4096);
          tma3d(sb + OFF_STG + 2048 * c, &P.tmQ, 16 * cl, 64 * rank, 2 * c, sbar);
        }
      }
      if (n >= 2) {
        fence_async();
        __syncwarp();
        if (lane == 0) { mbar_arrive(BAR(isH ? B_H : B_XT)); STAMP(3, (isH ? 17 : 13) + hw); }
      }
    }
#define SLOT(tab, kb) (sb + ((uint32_t)((tab) >> (4 * (kb))) & 15) * 16384)
#define LOAD_B(kb) tma4d(SLOT(SLOT_B, kb), &P.tmWo, 0, ((kb) >> 3) * 32, 2 * ((kb) & 7), 4 * cb + 2 * rank, BAR(B_FULL2 + (kb)))
#define LOAD_A(kb) bulk_ld_mc(SLOT(SLOT_A, kb) + rank * 8192, P.o + (rb * 16 + (kb)) * 1024 + rank * 512, 8192, BAR(B_FULL2 + (kb)))
    asm volatile("setmaxnreg.inc.sync.aligned.u32 104;");
    const unsigned epoch = *(volatile unsigned*)(smem + OFF_EPOCH);
    const uint32_t tag = ~epoch & 1;
    const int pi = hw < 2 ? 64 * mb - 288 + tid : 512 + 2 * mb + (lane & 1);
    const float* psrc = P.part + hp * 8 * 2176 + 4 * pi;
    uint4 f[8];
    {
      const uint32_t s16 = (sb & 0x3FFFF) >> 4;
      const int t = tid & 127, c = 2 + (warp & 1) + 2 * (warp & 2);
      uint32_t v[32];
      const uint4* hp4 = (const uint4*)(P.h + (blockIdx.x * 8 + c) * 2048) + ((lane & 15) * 2 + (lane >> 4));
#pragma unroll
      for (int i = 0; i < 8; i++) { const uint4 u = ld_nc4(hp4 + i * 32); v[4 * i] = u.x; v[4 * i + 1] = u.y; v[4 * i + 2] = u.z; v[4 * i + 3] = u.w; }
      float kva[36];
#pragma unroll
      for (int mt = 0; mt < 2; mt++) {
        mbar_wait(BAR(B_PKRDY + mt), 0);
        wg_fence();
#pragma unroll
        for (int ks = 0; ks < 8; ks++) {
          const uint32_t o = (ks >> 2) * 1024 + mt * 512 + (ks & 3) * 128, vb = (2 * STAGE_BYTES >> 4) + o;
          wgmma_ss_n72<1, 1>(kva, dsc(s16 + o + (1 << 16), SW128), dsc(s16 + vb + (((OFF_ONES >> 4) - vb) << 16), SW128), (mt | ks) != 0);
        }
        wg_commit();
      }
      float* pdst = P.part + (hp * 8 + mb) * 2176 + t * 4;
      float* zdst = P.part + (hp * 8 + mb) * 2176 + 2048 + (t >> 1);
      asm volatile("" : "+l"(pdst), "+l"(zdst));
      wg_wait<0>();
      keep(kva);
      if (hw < 1) {
#pragma unroll
        for (int c = 0; c < 4; c++) st_tag4(pdst + c * 512, kva[4 * c], kva[4 * c + 1], kva[4 * c + 2], kva[4 * c + 3], tag);
      } else {
#pragma unroll
        for (int c = 4; c < 8; c++) st_tag4(pdst + (c - 4) * 512, kva[4 * c], kva[4 * c + 1], kva[4 * c + 2], kva[4 * c + 3], tag);
      }
      const float z2 = __shfl_down_sync(~0u, kva[32], 4), z3 = __shfl_down_sync(~0u, kva[34], 4);
      if (!(lane & 7)) st_tag4(zdst, kva[32], kva[34], z2, z3, tag);
      if (lane == 0) mbar_arrive(BAR(B_PKFREE));
      if (hw == 0 && lane == 0) STAMP(3, 24);
      const float f0 = __uint_as_float(v[0] << 16) + (lane == 0 ? *(const float*)(smem + OFF_D + 4 * c) : 0.f);
      const int e = norm_exp(v, f0);
      if (HSPL > 0) norm_cvt<0, HSPL>(v, f0, e);
      if (hw >= 0) {
        if (hw == 0 && lane == 0) STAMP(3, 20);
#pragma unroll
        for (int p = 0; p < 8; p++) f[p] = ld_rlx4(psrc + p * 2176);
      }
      if (HSPL < 32) norm_cvt<HSPL, 32>(v, f0, e);
      uint8_t* dst = smem + OFF_H + 16384 + (warp & 3) * 4096 + (lane >> 4) * 512 + (lane & 15) * 16;
#pragma unroll
      for (int i = 0; i < 8; i++)
        *(uint4*)(dst + (i >> 1) * 1024 + (i & 1) * 256) = make_uint4(v[4 * i], v[4 * i + 1], v[4 * i + 2], v[4 * i + 3]);
      if (lane < 2) st_async(mapa(sb + OFF_SCALE + (8 * rank + c) * 4, lane), min(max(e + smem[OFF_EX + c] - 124, 1), 254) << 23, mapa(BAR(B_Y), lane));
      fence_async();
      __syncwarp();
      if (lane == 0) mbar_arrive(BAR(B_H2));
    }
    if (warp == 8) {
      mbar_wait(BAR(B_PKFREE), 0);
      {
        const uint32_t c0 = clock();
#pragma unroll 1
        for (int i = 0; i < 14; i++) {
          const int kb = i >> 1;
          while (__any_sync(~0u, (uint32_t)clock() - c0 < i * BPACE)) __nanosleep(32);
          if (elect_one()) {
            if (!(i & 1)) mbar_expect(BAR(B_FULL2 + kb), 16384);
            tma4d(SLOT(SLOT_B, kb) + (i & 1) * 8192, &P.tmWo1, 0, 0, 2 * kb, 4 * cb + 2 * rank + (i & 1), BAR(B_FULL2 + kb));
            if (i == 0) mbar_expect(BAR(B_Q), 8192);
            if (i < 4) tma3d(sb + OFF_SPARE + 2048 * i, &P.tmQ, 16 * cl, 64 * rank + 32 * (i >> 1), 2 * ((i + 6) & 7), BAR(B_Q));
          }
        }
      }
      if (lane == 0) STAMP(2, 2);
      mbar_wait(BAR(B_AFREE), 0);
      if (elect_one()) mbar_expect(BAR(B_FULL2), 16384);
      {
        const uint32_t dst = SLOT(SLOT_A, 0) + rank * 8192;
        const uint4* src = P.o + rb * 16 * 1024 + rank * 512;
        poll_ge(&P.ocnt[rb * 32], 16 * (epoch + 1));
        asm volatile("fence.proxy.async.global;" ::: "memory");
        if (lane == 0) STAMP(2, 3);
        if (elect_one()) bulk_ld_mc(dst, src, 8192, BAR(B_FULL2));
        if (lane == 0) STAMP(3, 23);
      }
#pragma unroll 1
      for (int kb = 1; kb < 7; kb++) {
        mbar_wait(BAR(kb < 3 ? B_AFREE + kb : B_CONS2 + ((kb - 3) >> 1)), 0);
        if (elect_one()) { mbar_expect(BAR(B_FULL2 + kb), 16384); LOAD_A(kb); }
      }
#pragma unroll 1
      for (int kb = 7; kb < 16; kb++) {
        mbar_wait(BAR(B_CONS2 + kb - 5), 0);
        if (kb == 8) mbar_wait(BAR(B_O1RDY), 0);
        if (elect_one()) { mbar_expect(BAR(B_FULL2 + kb), 32768); LOAD_A(kb); LOAD_B(kb); }
      }
      if (lane == 0) { P.epoch[blockIdx.x] = epoch + 1; STAMP(2, 5); }
    } else {
      {
#pragma unroll 1
        for (int n = 0; __any_sync(~0u, stale8(f, tag) & 1); n++) {
#pragma unroll
          for (int p = 0; p < 8; p++) ld_stale4(f[p], psrc + p * 2176, tag);
          if (n > SPIN_LIMIT) __trap();
        }
        float s0 = 0.f, s1 = 0.f, s2 = 0.f, s3 = 0.f;
#pragma unroll
        for (int p = 0; p < 8; p++) { s0 += __uint_as_float(f[p].x); s1 += __uint_as_float(f[p].y); s2 += __uint_as_float(f[p].z); s3 += __uint_as_float(f[p].w); }
        if (hw < 2 || lane < 2) st_tag4(P.kv + hp * 2176 + (4 * pi), s0, s1, s2, s3, tag);
      }
      if (lane == 0 && hw == 0) STAMP(3, 8);
      if (hw == 2) {
        unsigned* cnt = P.ocnt + (2 * mb + lane) * 32;
#pragma unroll 1
        for (int hh = 0; hh < 2; hh++) {
          mbar_wait(BAR(hh ? B_ODONE1 : B_ODONE), 0);
          if (lane < 2) asm volatile("red.release.gpu.global.add.u32 [%0], 1;" ::"l"(cnt + hh * 512) : "memory");
          if (lane == 0) STAMP(3, hh ? 6 : 7);
        }
        poll_ge(&P.ocnt[512 + rb * 32], 16 * (epoch + 1));
        asm volatile("fence.proxy.async.global;" ::: "memory");
        if (lane == 0) { mbar_arrive(BAR(B_O1RDY)); STAMP(2, 4); }
        __syncwarp();
      } else {
        if (PD2) __nanosleep(PD2);
        const int t = tid - 288;
        const float* src = P.kv + hp * 2176 + (4 * t);
        const float* zsrc = P.kv + hp * 2176 + (2048 + (t & 48) + 2 * (lane & 6));
        uint4 zp = ld_rlx4(zsrc);
#pragma unroll
        for (int p = 0; p < 8; p++) f[p] = ld_rlx4(src + 4 * ((p & 3) * 128 + (p >> 2) * 64));
        if (!opaque_true()) __trap();
#pragma unroll 1
        for (int n = 0; __any_sync(~0u, (stale8(f, tag) | (zp.x ^ tag)) & 1); n++) {
          ld_stale4(zp, zsrc, tag);
#pragma unroll
          for (int p = 0; p < 8; p++) ld_stale4(f[p], src + 4 * ((p & 3) * 128 + (p >> 2) * 64), tag);
          if (n > SPIN_LIMIT) __trap();
        }
#define PK2U(a, b) pk2(__uint_as_float(a), __uint_as_float(b))
        const uint32_t zf = (lane & 1) ? ((lane & 8) ? zp.w : zp.z) : ((lane & 8) ? zp.y : zp.x);
        const uint32_t zz = PK2U(zf, zf);
        *(uint4*)(smem + OFF_KVB + hw * 2560 + 2048 + lane * 16) = make_uint4(zz, zz, zz, zz);
        if (!opaque_true()) __trap();
#pragma unroll
        for (int hh = 0; hh < 2; hh++) {
          const uint4* ff = &f[4 * hh];
          uint8_t* dst = smem + OFF_KVB + hh * 2560 + q * 512 + (16 * hw + g) * 16;
          *(uint4*)dst = make_uint4(PK2U(ff[0].x, ff[0].y), PK2U(ff[1].x, ff[1].y), PK2U(ff[2].x, ff[2].y), PK2U(ff[3].x, ff[3].y));
          *(uint4*)(dst + 128) = make_uint4(PK2U(ff[0].z, ff[0].w), PK2U(ff[1].z, ff[1].w), PK2U(ff[2].z, ff[2].w), PK2U(ff[3].z, ff[3].w));
        }
        fence_async();
        __syncwarp();
        if (lane == 0) { mbar_arrive(BAR(B_KV)); if (hw == 0) STAMP(3, 9); }
      }
#define QBUF(ci) (sb + 2048 * (ci) + ((ci) < 6 ? OFF_STG : (ci) < 10 ? OFF_SPARE - 6 * 2048 : OFF_F2F - 10 * 2048))
      mbar_wait(BAR(B_Y), 0);
      if (elect_one()) {
        mbar_expect(sbar + 8, 4096);
#pragma unroll 1
        for (int ci = hw ? hw + 9 : 12; ci < 16; ci += 3) tma3d(QBUF(ci), &P.tmQ, 16 * cl, 64 * rank + 32, 2 * (ci & 7), sbar + 8);
      }
      mbar_wait(BAR(B_Q), 0);
      mbar_wait(sbar, hw == 0);
      {
        const float2 sc0 = *(const float2*)(smem + OFF_SCALE + 8 * q), sc1 = *(const float2*)(smem + OFF_SCALE + 32 + 8 * q);
        const uint32_t yl = sb + OFF_XT + (lane & 7) * XT_STRIDE + (lane >> 3) * 16;
#pragma unroll 1
        for (int ci = hw; ci < 16; ci += 3) {
          const uint32_t qb = QBUF(ci);
          if (ci >= 10) mbar_wait(sbar + 8, 1);
#pragma unroll 1
          for (int nl = 0; nl < 2; nl++) {
            uint32_t yy[2][4], qq[2][4];
            const uint32_t qa = qb + lane * 32 + ((lane & 4) << 2) + nl * 1024;
#pragma unroll
            for (int cg = 0; cg < 2; cg++) { ldsm4t(yy[cg], yl + cg * 2048 + (2 * ci + nl) * 64); ldsm4(qq[cg], qa ^ (cg * 16)); }
#pragma unroll
            for (int cg = 0; cg < 2; cg++) {
              const float2 sc = cg ? sc1 : sc0;
#pragma unroll
              for (int m = 0; m < 4; m++) {
                const float2 f = __half22float2(*(const __half2*)&yy[cg][m]);
                qq[cg][m] = hmul(qq[cg][m], pk2(f.x * sc.x, f.y * sc.y));
              }
              stsm4(qa ^ (cg * 16), qq[cg][0], qq[cg][1], qq[cg][2], qq[cg][3]);
            }
          }
          fence_async();
          __syncwarp();
          if (elect_one()) tma3d_st(&P.tmOA, qb, 16 * cl, 64 * rank + 32 * (ci >> 3), 2 * (ci & 7));
        }
        asm volatile("cp.async.bulk.commit_group;\ncp.async.bulk.wait_group.read 0;" ::: "memory");
      }
      if (lane == 0) STAMP(3, 10 + hw);
    }
  }
}

typedef CUresult (*EncodeFn)(CUtensorMap*, CUtensorMapDataType, cuuint32_t, void*, const cuuint64_t*, const cuuint64_t*,
                             const cuuint32_t*, const cuuint32_t*, CUtensorMapInterleave, CUtensorMapSwizzle,
                             CUtensorMapL2promotion, CUtensorMapFloatOOBfill);

static void enc(EncodeFn fn, CUtensorMap* m, const void* p, int rank, const cuuint64_t* dims, const cuuint64_t* strides,
                const cuuint32_t* box, CUtensorMapSwizzle swz, CUtensorMapL2promotion promo) {
  cuuint32_t es[4] = {1, 1, 1, 1};
  fn(m, CU_TENSOR_MAP_DATA_TYPE_BFLOAT16, rank, (void*)p, dims, strides, box, es, CU_TENSOR_MAP_INTERLEAVE_NONE, swz, promo,
     CU_TENSOR_MAP_FLOAT_OOB_FILL_NONE);
}

extern "C" void kernel_launch(void* const* d_in, const int* in_sizes, int n_in, void* d_out, int out_size) {
  void* fp = nullptr;
  cudaDriverEntryPointQueryResult qr;
  cudaGetDriverEntryPoint("cuTensorMapEncodeTiled", &fp, cudaEnableDefault, &qr);
  EncodeFn fn = (EncodeFn)fp;
  Params P;
  P.shift_k = (const __nv_bfloat16*)d_in[3]; P.h = (const __nv_bfloat16*)d_in[4]; P.D = (const __nv_bfloat16*)d_in[5];
  P.q = (const __nv_bfloat16*)d_in[0];
  cudaGetSymbolAddress((void**)&P.part, g_part); cudaGetSymbolAddress((void**)&P.kv, g_kv); cudaGetSymbolAddress((void**)&P.o, g_o);
  cudaGetSymbolAddress((void**)&P.ocnt, g_ocnt); cudaGetSymbolAddress((void**)&P.epoch, g_epoch);
  cudaGetSymbolAddress((void**)&P.thr, c_thr); cudaGetSymbolAddress((void**)&P.img, c_img);
  P.x = (const __nv_bfloat16*)d_in[6]; P.w = (const __nv_bfloat16*)d_in[7]; P.wo = (const __nv_bfloat16*)d_in[8];
  const CUtensorMapSwizzle S128 = CU_TENSOR_MAP_SWIZZLE_128B, S32 = CU_TENSOR_MAP_SWIZZLE_32B;
  const CUtensorMapL2promotion P0 = CU_TENSOR_MAP_L2_PROMOTION_NONE, P128 = CU_TENSOR_MAP_L2_PROMOTION_L2_128B;
  { cuuint64_t d[2] = {1024, 2048}, s[1] = {2048}; cuuint32_t b[2] = {64, 128}; enc(fn, &P.tmX, d_in[6], 2, d, s, b, S128, P128); }
  { cuuint64_t d[3] = {1024, 1024, 3}, s[2] = {6144, 2048}; cuuint32_t b[3] = {64, 64, 3}; enc(fn, &P.tmW, d_in[7], 3, d, s, b, S128, P128); }
  { cuuint64_t d[4] = {64, 64, 16, 16}, s[3] = {2048, 131072, 128}; cuuint32_t b[4] = {64, 32, 2, 2}; enc(fn, &P.tmWo, d_in[8], 4, d, s, b, S128, P128); }
  { cuuint64_t d[4] = {64, 64, 16, 16}, s[3] = {2048, 131072, 128}; cuuint32_t b[4] = {64, 32, 2, 1}; enc(fn, &P.tmWo1, d_in[8], 4, d, s, b, S128, P128); }
  { cuuint64_t d[2] = {1024, 2048}, s[1] = {2048}; cuuint32_t b[2] = {16, 72}; enc(fn, &P.tmK, d_in[1], 2, d, s, b, S32, PKV); }
  { cuuint64_t d[2] = {1024, 2048}, s[1] = {2048}; cuuint32_t b[2] = {16, 64}; enc(fn, &P.tmV, d_in[2], 2, d, s, b, S32, PKV); }
  { cuuint64_t d[3] = {1024, 128, 16}, s[2] = {32768, 2048}; cuuint32_t b[3] = {16, 32, 2}; enc(fn, &P.tmQ, d_in[0], 3, d, s, b, S32, PKV); }
  { cuuint64_t d[3] = {1024, 128, 16}, s[2] = {65536, 4096}; cuuint32_t b[3] = {16, 32, 2}; enc(fn, &P.tmOA, d_out, 3, d, s, b, S32, P0); }
  { cuuint64_t d[2] = {2048, 2048}, s[1] = {4096}; cuuint32_t b[2] = {64, 16}; enc(fn, &P.tmOB, d_out, 2, d, s, b, S128, P0); }
  cudaFuncSetAttribute(fused_kernel, cudaFuncAttributeMaxDynamicSharedMemorySize, SMEM_TOTAL);
  fused_kernel<<<128, 384, SMEM_TOTAL>>>(P);
}
```

```cpp
#include <cuda_runtime.h>
#include <cuda_bf16.h>
#include <cuda_fp16.h>
#include <cuda.h>
#include <stdint.h>

template<int TA, int TB, int SA=1> __device__ __forceinline__ void wgmma_ss_n192(float (&d)[96], uint64_t da, uint64_t db, int scale_d) {
  asm volatile("{\n.reg .pred p;\nsetp.ne.b32 p, %98, 0;\n"
    "wgmma.mma_async.sync.aligned.m64n192k16.f32.bf16.bf16 {%0, %1, %2, %3, %4, %5, %6, %7, %8, %9, %10, %11, %12, %13, %14, %15, %16, %17, %18, %19, %20, %21, %22, %23, %24, %25, %26, %27, %28, %29, %30, %31, %32, %33, %34, %35, %36, %37, %38, %39, %40, %41, %42, %43, %44, %45, %46, %47, %48, %49, %50, %51, %52, %53, %54, %55, %56, %57, %58, %59, %60, %61, %62, %63, %64, %65, %66, %67, %68, %69, %70, %71, %72, %73, %74, %75, %76, %77, %78, %79, %80, %81, %82, %83, %84, %85, %86, %87, %88, %89, %90, %91, %92, %93, %94, %95}, %96, %97, p, %101, 1, %99, %100;\n}\n"
    : "+f"(d[0]), "+f"(d[1]), "+f"(d[2]), "+f"(d[3]), "+f"(d[4]), "+f"(d[5]), "+f"(d[6]), "+f"(d[7]), "+f"(d[8]), "+f"(d[9]), "+f"(d[10]), "+f"(d[11]), "+f"(d[12]), "+f"(d[13]), "+f"(d[14]), "+f"(d[15]), "+f"(d[16]), "+f"(d[17]), "+f"(d[18]), "+f"(d[19]), "+f"(d[20]), "+f"(d[21]), "+f"(d[22]), "+f"(d[23]), "+f"(d[24]), "+f"(d[25]), "+f"(d[26]), "+f"(d[27]), "+f"(d[28]), "+f"(d[29]), "+f"(d[30]), "+f"(d[31]), "+f"(d[32]), "+f"(d[33]), "+f"(d[34]), "+f"(d[35]), "+f"(d[36]), "+f"(d[37]), "+f"(d[38]), "+f"(d[39]), "+f"(d[40]), "+f"(d[41]), "+f"(d[42]), "+f"(d[43]), "+f"(d[44]), "+f"(d[45]), "+f"(d[46]), "+f"(d[47]), "+f"(d[48]), "+f"(d[49]), "+f"(d[50]), "+f"(d[51]), "+f"(d[52]), "+f"(d[53]), "+f"(d[54]), "+f"(d[55]), "+f"(d[56]), "+f"(d[57]), "+f"(d[58]), "+f"(d[59]), "+f"(d[60]), "+f"(d[61]), "+f"(d[62]), "+f"(d[63]), "+f"(d[64]), "+f"(d[65]), "+f"(d[66]), "+f"(d[67]), "+f"(d[68]), "+f"(d[69]), "+f"(d[70]), "+f"(d[71]), "+f"(d[72]), "+f"(d[73]), "+f"(d[74]), "+f"(d[75]), "+f"(d[76]), "+f"(d[77]), "+f"(d[78]), "+f"(d[79]), "+f"(d[80]), "+f"(d[81]), "+f"(d[82]), "+f"(d[83]), "+f"(d[84]), "+f"(d[85]), "+f"(d[86]), "+f"(d[87]), "+f"(d[88]), "+f"(d[89]), "+f"(d[90]), "+f"(d[91]), "+f"(d[92]), "+f"(d[93]), "+f"(d[94]), "+f"(d[95])
    : "l"(da), "l"(db), "r"(scale_d), "n"(TA), "n"(TB), "n"(SA));
}
template<int TA, int TB, int SA=1> __device__ __forceinline__ void wgmma_ss_n128(float (&d)[64], uint64_t da, uint64_t db, int scale_d) {
  asm volatile("{\n.reg .pred p;\nsetp.ne.b32 p, %66, 0;\n"
    "wgmma.mma_async.sync.aligned.m64n128k16.f32.bf16.bf16 {%0, %1, %2, %3, %4, %5, %6, %7, %8, %9, %10, %11, %12, %13, %14, %15, %16, %17, %18, %19, %20, %21, %22, %23, %24, %25, %26, %27, %28, %29, %30, %31, %32, %33, %34, %35, %36, %37, %38, %39, %40, %41, %42, %43, %44, %45, %46, %47, %48, %49, %50, %51, %52, %53, %54, %55, %56, %57, %58, %59, %60, %61, %62, %63}, %64, %65, p, %69, 1, %67, %68;\n}\n"
    : "+f"(d[0]), "+f"(d[1]), "+f"(d[2]), "+f"(d[3]), "+f"(d[4]), "+f"(d[5]), "+f"(d[6]), "+f"(d[7]), "+f"(d[8]), "+f"(d[9]), "+f"(d[10]), "+f"(d[11]), "+f"(d[12]), "+f"(d[13]), "+f"(d[14]), "+f"(d[15]), "+f"(d[16]), "+f"(d[17]), "+f"(d[18]), "+f"(d[19]), "+f"(d[20]), "+f"(d[21]), "+f"(d[22]), "+f"(d[23]), "+f"(d[24]), "+f"(d[25]), "+f"(d[26]), "+f"(d[27]), "+f"(d[28]), "+f"(d[29]), "+f"(d[30]), "+f"(d[31]), "+f"(d[32]), "+f"(d[33]), "+f"(d[34]), "+f"(d[35]), "+f"(d[36]), "+f"(d[37]), "+f"(d[38]), "+f"(d[39]), "+f"(d[40]), "+f"(d[41]), "+f"(d[42]), "+f"(d[43]), "+f"(d[44]), "+f"(d[45]), "+f"(d[46]), "+f"(d[47]), "+f"(d[48]), "+f"(d[49]), "+f"(d[50]), "+f"(d[51]), "+f"(d[52]), "+f"(d[53]), "+f"(d[54]), "+f"(d[55]), "+f"(d[56]), "+f"(d[57]), "+f"(d[58]), "+f"(d[59]), "+f"(d[60]), "+f"(d[61]), "+f"(d[62]), "+f"(d[63])
    : "l"(da), "l"(db), "r"(scale_d), "n"(TA), "n"(TB), "n"(SA));
}
template<int TA, int TB, int SA=1> __device__ __forceinline__ void wgmma_ss_n72(float (&d)[36], uint64_t da, uint64_t db, int scale_d) {
  asm volatile("{\n.reg .pred p;\nsetp.ne.b32 p, %38, 0;\n"
    "wgmma.mma_async.sync.aligned.m64n72k16.f32.bf16.bf16 {%0, %1, %2, %3, %4, %5, %6, %7, %8, %9, %10, %11, %12, %13, %14, %15, %16, %17, %18, %19, %20, %21, %22, %23, %24, %25, %26, %27, %28, %29, %30, %31, %32, %33, %34, %35}, %36, %37, p, %41, 1, %39, %40;\n}\n"
    : "+f"(d[0]), "+f"(d[1]), "+f"(d[2]), "+f"(d[3]), "+f"(d[4]), "+f"(d[5]), "+f"(d[6]), "+f"(d[7]), "+f"(d[8]), "+f"(d[9]), "+f"(d[10]), "+f"(d[11]), "+f"(d[12]), "+f"(d[13]), "+f"(d[14]), "+f"(d[15]), "+f"(d[16]), "+f"(d[17]), "+f"(d[18]), "+f"(d[19]), "+f"(d[20]), "+f"(d[21]), "+f"(d[22]), "+f"(d[23]), "+f"(d[24]), "+f"(d[25]), "+f"(d[26]), "+f"(d[27]), "+f"(d[28]), "+f"(d[29]), "+f"(d[30]), "+f"(d[31]), "+f"(d[32]), "+f"(d[33]), "+f"(d[34]), "+f"(d[35])
    : "l"(da), "l"(db), "r"(scale_d), "n"(TA), "n"(TB), "n"(SA));
}
template<int TB, int SA=1> __device__ __forceinline__ void wgmma_rs_n40(float (&d)[20], uint32_t a0, uint32_t a1, uint32_t a2, uint32_t a3, uint64_t db, int scale_d) {
  asm volatile("{\n.reg .pred p;\nsetp.ne.b32 p, %25, 0;\n"
    "wgmma.mma_async.sync.aligned.m64n40k16.f32.bf16.bf16 {%0, %1, %2, %3, %4, %5, %6, %7, %8, %9, %10, %11, %12, %13, %14, %15, %16, %17, %18, %19}, {%20, %21, %22, %23}, %24, p, %27, 1, %26;\n}\n"
    : "+f"(d[0]), "+f"(d[1]), "+f"(d[2]), "+f"(d[3]), "+f"(d[4]), "+f"(d[5]), "+f"(d[6]), "+f"(d[7]), "+f"(d[8]), "+f"(d[9]), "+f"(d[10]), "+f"(d[11]), "+f"(d[12]), "+f"(d[13]), "+f"(d[14]), "+f"(d[15]), "+f"(d[16]), "+f"(d[17]), "+f"(d[18]), "+f"(d[19])
    : "r"(a0), "r"(a1), "r"(a2), "r"(a3), "l"(db), "r"(scale_d), "n"(TB), "n"(SA));
}
template<int TB> __device__ __forceinline__ void wgmma_hrs_n64(uint32_t (&d)[16], uint32_t a0, uint32_t a1, uint32_t a2, uint32_t a3, uint64_t db, int scale_d) {
  asm volatile("{\n.reg .pred p;\nsetp.ne.b32 p, %21, 0;\n"
    "wgmma.mma_async.sync.aligned.m64n64k16.f16.f16.f16 {%0, %1, %2, %3, %4, %5, %6, %7, %8, %9, %10, %11, %12, %13, %14, %15}, {%16, %17, %18, %19}, %20, p, 1, 1, %22;\n}\n"
    : "+r"(d[0]), "+r"(d[1]), "+r"(d[2]), "+r"(d[3]), "+r"(d[4]), "+r"(d[5]), "+r"(d[6]), "+r"(d[7]), "+r"(d[8]), "+r"(d[9]), "+r"(d[10]), "+r"(d[11]), "+r"(d[12]), "+r"(d[13]), "+r"(d[14]), "+r"(d[15])
    : "r"(a0), "r"(a1), "r"(a2), "r"(a3), "l"(db), "r"(scale_d), "n"(TB));
}
template<int TB> __device__ __forceinline__ void wgmma_hrs_n32(uint32_t (&d)[8], uint32_t a0, uint32_t a1, uint32_t a2, uint32_t a3, uint64_t db, int scale_d) {
  asm volatile("{\n.reg .pred p;\nsetp.ne.b32 p, %13, 0;\n"
    "wgmma.mma_async.sync.aligned.m64n32k16.f16.f16.f16 {%0, %1, %2, %3, %4, %5, %6, %7}, {%8, %9, %10, %11}, %12, p, 1, 1, %14;\n}\n"
    : "+r"(d[0]), "+r"(d[1]), "+r"(d[2]), "+r"(d[3]), "+r"(d[4]), "+r"(d[5]), "+r"(d[6]), "+r"(d[7])
    : "r"(a0), "r"(a1), "r"(a2), "r"(a3), "l"(db), "r"(scale_d), "n"(TB));
}

__device__ __align__(128) const uint32_t c_thr[1536] = {
  0x33fb33ff,0xa49c9de4,0x33273352,0xaf2cae76,0x33e233f1,0xa96ca7bd,0x32c432f7,0xb045afdd,0x33b733cf,0xac3eaaf7,0x3250328c,0xb0eab099,
  0x3378339a,0xadbcacff,0x31cd3211,0xb182b137,0x33d033fb,0xaadea46a,0x299e2d17,0xb3e0b396,0x32fb337a,0xafd2adb1,0xa78b1f76,0xb3f2b3ff,
  0x318b3254,0xb1c5b0e5,0xae6bac32,0xb354b3b8,0x2f4230a3,0xb321b285,0xb133b040,0xb215b2c7,0x337c33f2,0xada5a759,0xb179afc8,0xb1d6b2fe,
  0x31463293,0xb204b08e,0xb394b2ba,0xad23b055,0x2b402f4e,0xb3cbb31e,0xb3e4b3f9,0x293ba533,0xac269c52,0xb3bab400,0xb258b357,0x30e02e5f,
  0x330133e5,0xafbda922,0xb3f3b3c9,0x2727ab59,0x2deb314a,0xb36fb200,0xb194b32f,0x31bc2f0a,0xacdb2084,0xb39fb3ff,0xa565aea4,0x33f93347,
  0xb2b6b0db,0xb05ab25c,0x30892c1a,0x329733bc,0x326033d4,0xb0d6aa94,0xb00ab29b,0x32e83084,0x20e82f64,0xb3feb318,0x2d8da597,0x338133f8,
  0xb1fcae48,0xb14fb35c,0x339031b8,0x2d3a3199,0xb3e6b3ae,0x2909ac7b,0x32d133f4,0xb030a6f5,0x319d33bf,0xb1b3ac02,0x2e3ca874,0x335e33ec,
  0xacc32b89,0xb3a3b3c6,0x33f83276,0x25c930b7,0xb3dcb1f8,0xaa01b154,0x30653335,0xb2b0aef4,0xb107b383,0x32392d81,0xafa6214d,0xb307b3fe,
  0x30bc33a5,0xb273acb7,0x33c5311b,0x2ba23229,0xb0cc94b6,0xb267b400,0x30153360,0xb2e1ae31,0xb385b3ab,0x2d76ac93,0xb166a691,0xb1e7b3f5,
  0x22deb06a,0x33fd32ac,0xb337b3da,0x2ee8aa19,0x2f853387,0xb310ad6a,0x322d33fe,0xb1162216,0xb2a9abd3,0xb06fb3c2,0xb07428a6,0xb2a5b3ea,
  0xb111b3e9,0x323128be,0xb30db3c3,0x2f90abba,0x31aa227a,0x31a633fd,0x2e25ad5e,0x33633389,0x2d6a3365,0xb387ae1a,0xa21631aa,0xb3feb1a6,
  0xb3c2af85,0xabd3b310,0xb3eab22d,0x28a6b116,0xa8beb2a9,0x33e9306f,0x2bbab074,0x33c332a5,0x33fd3111,0x227a3231,0x3389330d,0xad5e2f90,
  0x2a63333f,0xb3d7aec6,0xb2a2a1b1,0xb07ab3fe,0xb3f7b158,0x25fbb1f4,0xacb7b38b,0x33a52d52,0x2e0eb025,0x336832d8,0x340030bc,0x14b63273,
  0x323533c0,0xb10c2beb,0xac9330cc,0xb3abb267,0x23433316,0xb3fdaf6f,0xb38eb225,0x2d46b11f,0xb342b29e,0x2ebbb07f,0x31e3aa7c,0x316b33d6,
  0x3264a6c3,0x30d133f5,0x2c0233ac,0xb3bfac87,0x28f0336a,0xb3e7ae02,0xb3c6b19d,0x2b89b1b3,0xa59732e8,0xb3f8b00a,0xaccfb3ed,0x33a1285b,
  0xb1b8b381,0x3199ad8d,0x336c31df,0xadf73170,0x33f42d3a,0x26f53390,0xb30423a7,0xafb2b3fc,0xb05f3030,0xb2b3b2d1,0x29e8b27a,0x33dd30b2,
  0xab5932b6,0xb3c9b05a,0x30adb089,0x327e3297,0xaf0ab3f3,0x332fa727,0x240633b0,0xb3fcac6f,0x33473194,0xaea431bc,0xb174b359,0x31daae54,
  0xb3bca565,0xac1ab3f9,0x33ee2f59,0xa842331b,0xaddf3281,0xb371b0a8,0x34002b40,0x1c5233cb,0xa759b3ef,0x33f22829,0xb2fe2c26,0xafc8b3ba,
  0x308e337c,0xb2932da5,0x3055b179,0x32ba31d6,0xb31eb146,0x2f4eb204,0xa5333394,0xb3f9ad23,0xaff33249,0xb2f1b0f3,0x30e532fb,0xb2542fd2,
  0x2b28b373,0x33cc2dd4,0xb285b18b,0x30a3b1c5,0x246a33fa,0xb3fba500,0x33962f42,0xad173321,0xadb1b3d0,0x337aaade,0xb3ffa99e,0x1f76b3e0,
  0xb0ee320d,0xb24db13c,0xac4b3398,0xb3b5ad0b,0x304ab289,0x32c1309e,0x2985b3ce,0x33e12b0f,0xaf3732f4,0xb324afe8,0xa4ce33f0,0xb3faa7ef,
  0x2dc8b34f,0x33762e82,0x9de4b3ff,0x33ff1ead,0xb1c931cd,0xb186b182,0xb3762e82,0xadc8b34f,0x324db13c,0x30ee320d,0x33b5ad0b,0x2c4b3398,
  0xb2c1309e,0xb04ab289,0xb3e12b0f,0xa985b3ce,0x3324afe8,0x2f3732f4,0x33faa7ef,0x24ce33f0,0xb285318b,0xb0a3b1c5,0xb2c7ae6b,0x3040b354,
  0x3396af42,0x2d173321,0x31413133,0xb2093215,0xb3ff299e,0x9f76b3e0,0xae8db2bd,0x334cb050,0x33b8278b,0xac3233f2,0x281033b3,0xb3ef2c57,
  0xb31e3146,0xaf4eb204,0xa533b394,0x33f9ad23,0x3400ab40,0x9c5233cb,0xae5f33e4,0xb357a93b,0xb2feac26,0x2fc8b3ba,0x3245b258,0x30f830e0,
  0x30553179,0xb2ba31d6,0xb3df2e99,0xa9b6b34a,0xb39230fd,0xad2fb241,0x3200b301,0x314a2fbd,0x337f1b11,0xad993400,0xb3ff2deb,0xa084b36f,
  0xb005b129,0x32ebb21d,0x325c2cdb,0xb0db339f,0xa92233de,0xb3e529cf,0xab59b2b6,0x33c9b05a,0xb3dd30b2,0xa9e8b27a,0x33d4ab71,0xaa9433c8,
  0x32212c0e,0xb12433bd,0xaf64b0d6,0x3318b260,0x197fb345,0x3400aeaf,0xae4833fe,0xb35c20e8,0xb23d3332,0xb102aeff,0x33aeb14f,0x2c7b31fc,
  0xb3fe3065,0xa14db2b0,0x2ebb307f,0xb342329e,0x300f2fa6,0xb2e53307,0x30d1b3f5,0x326426c3,0x302ab400,0x32d517db,0xb3e72e02,0x28f0b36a,
  0xb3fd2f6f,0x2343b316,0x2d46311f,0xb38e3225,0xb3f53015,0x2691b2e1,0xaf9b33eb,0xb30a288d,0x2a193166,0xb3da31e7,0x33d7aec6,0xaa63333f,
  0x3313b337,0x2f7a2ee8,0xa5fbb1f4,0x33f7b158,0xb1a1a8d7,0x31afb3e8,0xb36832d8,0xae0eb025,0xb3c22f85,0x2bd3b310,0xb3ea322d,0xa8a6b116,
  0xa8be32a9,0xb3e9306f,0x2bba3074,0xb3c332a5,0x33fdb111,0xa27a3231,0x3389b30d,0x2d5e2f90,0xa216b1aa,0x33feb1a6,0xaed2ae25,0x333db363,
  0xb3652edd,0x2e1ab33a,0xb1aa227a,0x31a6b3fd,0xaf853387,0xb3102d6a,0xb22d33fe,0xb116a216,0x32a9abd3,0xb06f33c2,0x307428a6,0xb2a533ea,
  0x3111b3e9,0x3231a8be,0x330db3c3,0x2f902bba,0xb2e12e31,0x3015b360,0x288db1a1,0x33ebb1af,0xb1e733f5,0xb1662691,0xb33f2f9b,0x2ec6b30a,
  0x2ee82a19,0xb33733da,0xb15833d7,0xb1f42a63,0x33e8b313,0x28d72f7a,0x302525fb,0xb2d833f7,0xb2392d81,0x3107b383,0x3307b3fe,0x2fa6214d,
  0xb35e33ec,0xae3ca874,0x97dbb00f,0x3400b2e5,0xa5c930b7,0xb3f83276,0xb316302a,0x2f6fb2d5,0x32b0aef4,0xb0653335,0xb29e33fd,0xb07f2343,
  0xb1702ccf,0x31dfb3a1,0x3345b124,0xaeaf3221,0xb3fc336c,0xa3a7adf7,0x3332b400,0x2eff997f,0xb0b23304,0xb27a2fb2,0x2b71b102,0x33c8b23d,
  0x2c0e29e8,0xb3bd33dd,0xb0d62a94,0x3260b3d4,0xb0892c1a,0x3297b3bc,0x2aad2842,0xb3d333ee,0xb3b0327e,0x2c6fb0ad,0x3241b035,0xb0fd32ce,
  0xb35933fc,0xae542406,0x3400b392,0x1b112d2f,0xaf5931da,0xb31b3174,0x321db37f,0x3129ad99,0xaf152ac6,0x332cb3d2,0xb1463293,0xb204308e,
  0xb281312e,0x30a8b219,0xab402f4e,0xb3cb331e,0xb3ef3371,0x2829addf,0x2c269c52,0xb3ba3400,0xb37c33f2,0xada52759,0x3179afc8,0xb1d632fe,
  0xacf32953,0x339cb3e3,0xb3fa33cc,0x2500ab28,0xb0942f21,0x3290b32a,0xb3d033fb,0xaade246a,0xb249317d,0x30f3b1d2,0xb2fb337a,0xafd22db1,
  0xb37332f1,0x2dd4aff3,0xb18b3254,0xb1c530e5,0xa96c27bd,0x33e2b3f1,0xb0452fdd,0x32c4b2f7,0xac3e2af7,0x33b7b3cf,0xb0ea3099,0x3250b28c,
  0xadbc2cff,0x3378b39a,0xb1823137,0x31cdb211,0xaf2c2e76,0x3327b352,0xb20d31c9,0x313cb186,0x313c3186,0xb20db1c9,0x2d0b2dc8,0xb398b376,
  0x309e30ee,0xb289b24d,0x2b0f2c4b,0xb3ceb3b5,0x2fe8304a,0xb2f4b2c1,0x27ef2985,0xb3f0b3e1,0x2e822f37,0xb34fb324,0x1ead24ce,0xb3ffb3fa,
  0xb2bdb209,0xb050b141,0xb290b32a,0x30942f21,0xb3b3b34c,0xac57ae8d,0xb0f3b1d2,0x3249317d,0xb400b3ef,0x1d1ba810,0xadd4aff3,0x337332f1,
  0xb39cb3e3,0x2cf32953,0xa500ab28,0x33fa33cc,0xae99b0f8,0x334a3245,0x33ff33b2,0x201f2c63,0x2438a9b6,0x33fc33df,0x332c33d2,0xaf15aac6,
  0x303a2ce7,0x32cb339e,0x30a83219,0xb281b12e,0x32ee31c0,0x2ffe3190,0x28292ddf,0xb3efb371,0x33b0327e,0x2c6f30ad,0xb241b035,0xb0fdb2ce,
  0x335933fc,0xae54a406,0xb400b392,0x1b11ad2f,0x2f5931da,0xb31bb174,0xb21db37f,0x31292d99,0xaaad2842,0xb3d3b3ee,0xa9cfb005,0x33de32eb,
  0x285b305f,0xb3edb2b3,0x2c0ea9e8,0x33bd33dd,0xb170accf,0xb1dfb3a1,0x33453124,0x2eaf3221,0xb3fcb36c,0x23a7adf7,0x33323400,0xaeff997f,
  0xb0b2b304,0x327a2fb2,0x2b713102,0xb3c8b23d,0xb400b2e5,0x17dbb00f,0x2e023264,0xb36ab0d1,0xaf6fb2d5,0x3316302a,0xb11fa8f0,0xb225b3e7,
  0x307f2343,0x329e33fd,0xb3d6b38e,0x2a7cad46,0x33f53342,0xa6c32ebb,0xac87b1e3,0x33ac316b,0x28d7af7a,0x33e83313,0xb2d8b3f7,0x3025a5fb,
  0x33eb31af,0x288d31a1,0x2bebae0e,0x33c03368,0x2ec6330a,0xb33faf9b,0x33fe3235,0x21b1310c,0xb1f4aa63,0xb158b3d7,0x2d5232a2,0xb38bb07a,
  0x33a7333d,0xacab2ed2,0x33f63162,0x262d31eb,0xaa4b301a,0xb3d8b2de,0x2a32326b,0xb3d9b0c7,0xb3f6b26f,0x265fb0c1,0xb3a9b020,0xac9fb2db,
  0x0e48b15d,0x340031f0,0xae1ab33a,0x33652edd,0xaed22e25,0xb33db363,0xb1eb0e48,0xb162b400,0xb2deb3a7,0x301aacab,0xb0c7b3f6,0x326b262d,
  0x30c1aa4b,0x326f33d8,0x32db2a32,0x302033d9,0x31f033f6,0xb15d265f,0x2edd33a9,0xb33aac9f,0xb2acb385,0x306aad76,0x2a19b166,0x33da31e7,
  0x3229a2de,0x311b33fd,0x33133337,0xaf7a2ee8,0x2e3133c5,0xb360aba2,0xb1a128d7,0xb1afb3e8,0xb3f5b015,0xa691b2e1,0xaf9bb3eb,0x330a288d,
  0x3154acc3,0x31f833a3,0x2ef433f8,0xb335a5c9,0x2d8133dc,0xb383aa01,0xb3feb065,0x214db2b0,0xb3ecb107,0x2874b239,0x300fafa6,0x32e53307,
  0x30b7ae3c,0x3276335e,0x302a3400,0xb2d517db,0x312433bd,0xb2212c0e,0xb318b260,0x2f64b0d6,0xb400aeaf,0x997fb345,0x335c20e8,0x2e4833fe,
  0x3102aeff,0x323d3332,0xac7b31fc,0xb3aeb14f,0x2a9433c8,0xb3d4ab71,0xb084b3e6,0x329ba909,0xb2ce2aad,0xb035b3d3,0x33e529cf,0x292233de,
  0x2d2fb241,0x339230fd,0xb14a2fbd,0xb200b301,0x2d993400,0xb37f1b11,0x2084b36f,0x33ff2deb,0xb2ebb21d,0x3005b129,0x30db339f,0xb25c2cdb,
  0xae5fb3e4,0x3357a93b,0xb190303a,0xb1c0b2cb,0x32453258,0xb0f830e0,0x2c63b2ee,0x33b22ffe,0xb3dfae99,0x29b6b34a,0x2ac633ff,0xb3d2a01f,
  0x339ea438,0x2ce733fc,0xb12eb32c,0x3219af15,0x33b8a78b,0x2c3233f2,0x2810b3b3,0x33ef2c57,0xb2c72e6b,0xb040b354,0x29533400,0xb3e31d1b,
  0x3141b133,0x32093215,0xaf21b39c,0x332aacf3,0xae8d32bd,0xb34cb050,0x317d3290,0xb1d23094,0x27bd33fb,0xb3f1249c,0x2fdd3327,0xb2f72f2c,
  0xaaf7b3e2,0x33cfa96c,0xb099b2c4,0x328cb045,0x2cff33b7,0xb39a2c3e,0x31373250,0xb21130ea,0xae76b378,0x3352adbc,0xb1c9b1cd,0x3186b182,
  0xb3ff1ead,0x1de4b3ff,0xb352adbc,0x2e76b378,0x33f1249c,0xa7bd33fb,0x32f72f2c,0xafdd3327,0xb3cfa96c,0x2af7b3e2,0xb28cb045,0x3099b2c4,
  0x339a2c3e,0xacff33b7,0x321130ea,0xb1373250,0x2953b400,0x33e31d1b,0x33ccadd4,0x2b283373,0xaf21339c,0xb32aacf3,0xb3fb2500,0x246ab3fa,
  0x317db290,0x31d23094,0x337a2ade,0xadb133d0,0xb2f130f3,0xaff3b249,0xb254afd2,0x30e5b2fb,0x339e2438,0xace733fc,0xb12e332c,0xb219af15,
  0xb190b03a,0x31c0b2cb,0x3371b0a8,0x2ddf3281,0x2c6332ee,0xb3b22ffe,0xb3f22829,0x2759b3ef,0x2ac6b3ff,0x33d2a01f,0x32932da5,0xb08e337c,
  0xaf0a33f3,0xb32fa727,0x2406b3b0,0x33fcac6f,0x3347b194,0x2ea431bc,0xb1743359,0xb1daae54,0xb3bc2565,0x2c1ab3f9,0x33eeaf59,0x2842331b,
  0x30ad3089,0xb27e3297,0xb2ceaaad,0x3035b3d3,0xb29ba909,0x3084b3e6,0x305f3030,0xb2b332d1,0x259732e8,0xb3f8300a,0x2ccfb3ed,0x33a1a85b,
  0x31b8b381,0x31992d8d,0xb36c31df,0xadf7b170,0xb3f42d3a,0x26f5b390,0x330423a7,0xafb233fc,0x316bb3d6,0x31e32a7c,0xb3832a01,0x2d81b3dc,
  0xb3bf2c87,0x2c02b3ac,0x28743239,0xb3ec3107,0x2b8931b3,0xb3c6319d,0x3276b35e,0x30b72e3c,0x31f8b3a3,0x31542cc3,0xb33525c9,0x2ef4b3f8,
  0x310c2beb,0xb23533c0,0x33abb267,0x2c9330cc,0x307ab3fe,0x32a2a1b1,0xb06aad76,0x32acb385,0xb3a52d52,0x2cb7b38b,0xb11b33fd,0xb229a2de,
  0x94b63273,0xb40030bc,0x3360aba2,0xae3133c5,0xb2de33a7,0xb01aacab,0xb0c733f6,0xb26b262d,0x30c12a4b,0xb26f33d8,0x32dbaa32,0xb02033d9,
  0x31f0b3f6,0x315d265f,0x2eddb3a9,0x333aac9f,0xb1eb8e48,0x3162b400,0xb3872e1a,0x2d6ab365,0xae25ad5e,0x3363b389,0x8e48b15d,0x3400b1f0,
  0xb3a7333d,0xacabaed2,0xb3f63162,0x262db1eb,0x2a4b301a,0xb3d832de,0xaa32326b,0xb3d930c7,0x33f6b26f,0x265f30c1,0x33a9b020,0xac9f32db,
  0x33c0b368,0x2beb2e0e,0x30cc94b6,0xb2673400,0x21b1b10c,0x33feb235,0x3385b3ab,0x2d762c93,0xb38b307a,0x2d52b2a2,0xa2deb06a,0x33fdb2ac,
  0xb0bc33a5,0xb2732cb7,0xb3c5311b,0x2ba2b229,0x26c32ebb,0xb3f53342,0xb3ac316b,0x2c87b1e3,0x336ab0d1,0xae023264,0xb19d33bf,0xb1b32c02,
  0x3225b3e7,0x311fa8f0,0x2cc32b89,0xb3a333c6,0xaa7cad46,0x33d6b38e,0x33dcb1f8,0xaa013154,0xb3fe3318,0x20e8af64,0x3381b3f8,0x2d8d2597,
  0xb14f335c,0xb1fc2e48,0x2d3ab199,0x3390b1b8,0x29092c7b,0xb3e633ae,0xb03026f5,0x32d1b3f4,0x32e8b084,0xb00a329b,0xb3ed32b3,0x285bb05f,
  0x29cfb005,0x33deb2eb,0xb05a325c,0xb2b630db,0xafbd2922,0x3301b3e5,0x27272b59,0xb3f333c9,0xb36f3200,0x2debb14a,0x31bcaf0a,0xb194332f,
  0xb39f33ff,0xacdba084,0x33f9b347,0xa5652ea4,0x3394b2ba,0xad233055,0xa438a9b6,0x33fcb3df,0x33e4b3f9,0x293b2533,0xb03a2ce7,0x32cbb39e,
  0x3258b357,0x30e0ae5f,0xb2ee31c0,0x2ffeb190,0x2e99b0f8,0x334ab245,0xb3ff33b2,0x201fac63,0xaf4230a3,0xb3213285,0x3133b040,0xb21532c7,
  0xa99e2d17,0xb3e03396,0x32bdb209,0xb0503141,0x278b1f76,0xb3f233ff,0x33b3b34c,0xac572e8d,0x2e6bac32,0xb35433b8,0x3400b3ef,0x1d1b2810,
  0xb289324d,0x309eb0ee,0xb3ce33b5,0x2b0fac4b,0xb2f432c1,0x2fe8b04a,0xb3f033e1,0x27efa985,0xb34f3324,0x2e82af37,0xb3ff33fa,0x1eada4ce,
  0xb3983376,0x2d0badc8,0xb3fb33ff,0xa49c1de4,0x351c35f6,0xac93a617,0xb8a3b93c,0x308d2a16,0x32f43448,0xb160afa5,0xb6a4b7fe,0x353a3389,
  0x2fa53160,0xb448b2f4,0xb389b53a,0x37fe36a4,0x26172c93,0xb5f6b51c,0xaa16b08d,0x393c38a3,0x34c3358c,0xac47a5b2,0xb85fb8f3,0x304229b1,
  0x327e33fd,0xb106af26,0xb63cb785,0x34e7330f,0x2f263106,0xb3fdb27e,0xb30fb4e7,0x3785363c,0x25b22c47,0xb58cb4c3,0xa9b1b042,0x38f3385f,
  0x346a3523,0xabf6a54d,0xb81ab8a8,0x2fef294d,0x3209336b,0xb0acaea7,0xb5d4b70a,0x34933294,0x2ea730ac,0xb36bb209,0xb294b493,0x370a35d4,
  0x254d2bf6,0xb523b46a,0xa94dafef,0x38a8381a,0x341334bc,0xab5fa4e9,0xb7a6b85a,0x2f5928e8,0x319432da,0xb052ae28,0xb56ab68d,0x343e3219,
  0x2e283052,0xb2dab194,0xb219b43e,0x368d356a,0x24e92b5f,0xb4bcb413,0xa8e8af59,0x385a37a6,0x33783456,0xaac8a484,0xb715b80a,0x2ec32884,
  0x3120324a,0xaff2ada9,0xb4ffb60e,0x33d3319e,0x2da92ff2,0xb24ab120,0xb19eb3d3,0x360e34ff,0x24842ac8,0xb456b378,0xa884aec3,0x380a3715,
  0x32cd33e3,0xaa31a420,0xb682b76f,0x2e2d281f,0x30ac31bb,0xaf3fad2a,0xb493b58d,0x33283122,0x2d2a2f3f,0xb1bbb0ac,0xb122b328,0x358d3493,
  0x24202a31,0xb3e3b2cd,0xa81fae2d,0x376f3682,0x3223331c,0xa999a376,0xb5ebb6c6,0x2d972776,0x3039312d,0xae8dacac,0xb426b50b,0x327c30a6,
  0x2cac2e8d,0xb12db039,0xb0a6b27c,0x350b3426,0x23762999,0xb31cb223,0xa776ad97,0x36c635eb,0x317a3257,0xa902a2ad,0xb552b61a,0x2d0026ad,
  0x2f8c309f,0xaddcac2e,0xb371b487,0x31cf3029,0x2c2e2ddc,0xb09faf8c,0xb029b1cf,0x34873371,0x22ad2902,0xb257b17a,0xa6adad00,0x361a3552,
  0x30d23194,0xa86ba1e4,0xb4b7b56a,0x2c6a25e4,0x2ea73012,0xad2aab5f,0xb294b402,0x31222f59,0x2b5f2d2a,0xb012aea7,0xaf59b122,0x34023294,
  0x21e4286b,0xb194b0d2,0xa5e4ac6a,0x356a34b7,0x302c30d2,0xa7a9a11b,0xb41ab4b7,0x2ba7251b,0x2dc22f0c,0xac79aa63,0xb1b6b2f7,0x30742e5f,
  0x2a632c79,0xaf0cadc2,0xae5fb074,0x32f731b6,0x211b27a9,0xb0d2b02c,0xa51baba7,0x34b7341a,0x2f0c3012,0xa67ba052,0xb2f7b402,0x2a7a2452,
  0x2cde2df5,0xab91a967,0xb0d7b1e8,0x2f8b2d65,0x29672b91,0xadf5acde,0xad65af8b,0x31e830d7,0x2052267b,0xb012af0c,0xa452aa7a,0x340232f7,
  0x2dc22ea7,0xa54d9f12,0xb1b6b294,0x294d2311,0x2bf62cde,0xaa31a86b,0xafefb0d7,0x2e2d2c6a,0x286b2a31,0xacdeabf6,0xac6aae2d,0x30d72fef,
  0x1f12254d,0xaea7adc2,0xa311a94d,0x329431b6,0x2c792d2a,0xa4209d7f,0xb074b122,0x281f217f,0x2a312b91,0xa8d0a6e0,0xae2daf8b,0x2cce2ade,
  0x26e028d0,0xab91aa31,0xaadeacce,0x2f8b2e2d,0x1d7f2420,0xad2aac79,0xa17fa81f,0x31223074,0x2a632b5f,0xa1e49bdb,0xae5faf59,0x25e41fdb,
  0x286b2967,0xa6e0a4e9,0xac6aad65,0x2ade28e8,0x24e926e0,0xa967a86b,0xa8e8aade,0x2d652c6a,0x1bdb21e4,0xab5faa63,0x9fdba5e4,0x2f592e5f,
  0x27a9286b,0x9f1298b6,0xaba7ac6a,0x23111cb6,0x254d267b,0xa420a1e4,0xa94daa7a,0x281f25e4,0x21e42420,0xa67ba54d,0xa5e4a81f,0x2a7a294d,
  0x18b61f12,0xa86ba7a9,0x9cb6a311,0x2c6a2ba7,0x211b21e4,0x98b69248,0xa51ba5e4,0x1cb61648,0x1f122052,0x9d7f9bdb,0xa311a452,0x217f1fdb,
  0x1bdb1d7f,0xa0529f12,0x9fdba17f,0x24522311,0x124818b6,0xa1e4a11b,0x96489cb6,0x25e4251b,0xa11ba1e4,0x18b61248,0x251b25e4,0x9cb69648,
  0x9f12a052,0x1d7f1bdb,0x23112452,0xa17f9fdb,0x9bdb9d7f,0x20521f12,0x1fdb217f,0xa452a311,0x924898b6,0x21e4211b,0x16481cb6,0xa5e4a51b,
  0xa7a9a86b,0x1f1218b6,0x2ba72c6a,0xa3119cb6,0xa54da67b,0x242021e4,0x294d2a7a,0xa81fa5e4,0xa1e4a420,0x267b254d,0x25e4281f,0xaa7aa94d,
  0x98b69f12,0x286b27a9,0x1cb62311,0xac6aaba7,0xaa63ab5f,0x21e41bdb,0x2e5f2f59,0xa5e49fdb,0xa86ba967,0x26e024e9,0x2c6a2d65,0xaadea8e8,
  0xa4e9a6e0,0x2967286b,0x28e82ade,0xad65ac6a,0x9bdba1e4,0x2b5f2a63,0x1fdb25e4,0xaf59ae5f,0xac79ad2a,0x24201d7f,0x30743122,0xa81fa17f,
  0xaa31ab91,0x28d026e0,0x2e2d2f8b,0xacceaade,0xa6e0a8d0,0x2b912a31,0x2ade2cce,0xaf8bae2d,0x9d7fa420,0x2d2a2c79,0x217f281f,0xb122b074,
  0xadc2aea7,0x254d1f12,0x31b63294,0xa94da311,0xabf6acde,0x2a31286b,0x2fef30d7,0xae2dac6a,0xa86baa31,0x2cde2bf6,0x2c6a2e2d,0xb0d7afef,
  0x9f12a54d,0x2ea72dc2,0x2311294d,0xb294b1b6,0xaf0cb012,0x267b2052,0x32f73402,0xaa7aa452,0xacdeadf5,0x2b912967,0x30d731e8,0xaf8bad65,
  0xa967ab91,0x2df52cde,0x2d652f8b,0xb1e8b0d7,0xa052a67b,0x30122f0c,0x24522a7a,0xb402b2f7,0xb02cb0d2,0x27a9211b,0x341a34b7,0xaba7a51b,
  0xadc2af0c,0x2c792a63,0x31b632f7,0xb074ae5f,0xaa63ac79,0x2f0c2dc2,0x2e5f3074,0xb2f7b1b6,0xa11ba7a9,0x30d2302c,0x251b2ba7,0xb4b7b41a,
  0xb0d2b194,0x286b21e4,0x34b7356a,0xac6aa5e4,0xaea7b012,0x2d2a2b5f,0x32943402,0xb122af59,0xab5fad2a,0x30122ea7,0x2f593122,0xb402b294,
  0xa1e4a86b,0x319430d2,0x25e42c6a,0xb56ab4b7,0xb17ab257,0x290222ad,0x3552361a,0xad00a6ad,0xaf8cb09f,0x2ddc2c2e,0x33713487,0xb1cfb029,
  0xac2eaddc,0x309f2f8c,0x302931cf,0xb487b371,0xa2ada902,0x3257317a,0x26ad2d00,0xb61ab552,0xb223b31c,0x29992376,0x35eb36c6,0xad97a776,
  0xb039b12d,0x2e8d2cac,0x3426350b,0xb27cb0a6,0xacacae8d,0x312d3039,0x30a6327c,0xb50bb426,0xa376a999,0x331c3223,0x27762d97,0xb6c6b5eb,
  0xb2cdb3e3,0x2a312420,0x3682376f,0xae2da81f,0xb0acb1bb,0x2f3f2d2a,0x3493358d,0xb328b122,0xad2aaf3f,0x31bb30ac,0x31223328,0xb58db493,
  0xa420aa31,0x33e332cd,0x281f2e2d,0xb76fb682,0xb378b456,0x2ac82484,0x3715380a,0xaec3a884,0xb120b24a,0x2ff22da9,0x34ff360e,0xb3d3b19e,
  0xada9aff2,0x324a3120,0x319e33d3,0xb60eb4ff,0xa484aac8,0x34563378,0x28842ec3,0xb80ab715,0xb413b4bc,0x2b5f24e9,0x37a6385a,0xaf59a8e8,
  0xb194b2da,0x30522e28,0x356a368d,0xb43eb219,0xae28b052,0x32da3194,0x3219343e,0xb68db56a,0xa4e9ab5f,0x34bc3413,0x28e82f59,0xb85ab7a6,
  0xb46ab523,0x2bf6254d,0x381a38a8,0xafefa94d,0xb209b36b,0x30ac2ea7,0x35d4370a,0xb493b294,0xaea7b0ac,0x336b3209,0x32943493,0xb70ab5d4,
  0xa54dabf6,0x3523346a,0x294d2fef,0xb8a8b81a,0xb4c3b58c,0x2c4725b2,0x385f38f3,0xb042a9b1,0xb27eb3fd,0x31062f26,0x363c3785,0xb4e7b30f,
  0xaf26b106,0x33fd327e,0x330f34e7,0xb785b63c,0xa5b2ac47,0x358c34c3,0x29b13042,0xb8f3b85f,0xb51cb5f6,0x2c932617,0x38a3393c,0xb08daa16,
  0xb2f4b448,0x31602fa5,0x36a437fe,0xb53ab389,0xafa5b160,0x344832f4,0x3389353a,0xb7feb6a4,0xa617ac93,0x35f6351c,0x2a16308d,0xb93cb8a3,
};
__device__ __align__(128) const uint32_t c_img[2560] = {
  0x326d31ed,0x333b32dd,0x33c33388,0x33fe33ea,0x33c331ed,0x31ed33c3,0xa8b22d64,0xb33bb0c4,0x33ea31ed,0xad64301d,0xb2ddb388,0x315fa8b2,
  0x32dd31ed,0xb3feabc6,0x326dad64,0xad64326d,0x30c431ed,0xaed7b2dd,0x2bc63388,0xa248b3ea,0x2bc631ed,0x315fb3c3,0xb3ea2d64,0x2ed730c4,
  0xa8b231ed,0x3388b01d,0x301db388,0xb1ed28b2,0xb01d31ed,0x22482bc6,0x30c4ad64,0x3388b26d,0x33ea33fe,0x338833c3,0x32dd333b,0x31ed326d,
  0xb2ddb3fe,0xa248b01d,0x326d2ed7,0x338833ea,0x30c433fe,0xb33babc6,0xabc6b33b,0x33fe30c4,0xabc6b3fe,0x31ed32dd,0xb3eaaed7,0x333ba8b2,
  0xa8b233fe,0x2d64b3c3,0xb01d333b,0x315fb26d,0x301db3fe,0xb3fe301d,0x30c42ed7,0x2d64b3ea,0xb26d33fe,0x2ed72bc6,0x33c3b33b,0xa248b0c4,
  0x33c3b3fe,0x315fb2dd,0x28b2aed7,0xaed728b2,0xb0c4b15f,0xaed7b01d,0xabc6ad64,0xa248a8b2,0xabc6b15f,0x315f2bc6,0x33ea3388,0x2ed7326d,
  0x28b2b15f,0x338832dd,0xb01d2d64,0xb1edb3ea,0x301db15f,0x224833c3,0xb0c4b388,0x338830c4,0x326db15f,0xb33b301d,0x33c3ad64,0xb3fe28b2,
  0x33c3b15f,0xb1edabc6,0xa8b23388,0x333bb26d,0x33eab15f,0x2d64b2dd,0xb2dd2d64,0xb15f33ea,0x32ddb15f,0x33feb3c3,0x326db388,0x2d64b0c4,
  0x28b22248,0x2d642bc6,0x301d2ed7,0x315f30c4,0xb01da248,0xb3feb2dd,0xb0c4b33b,0x2d64a8b2,0x326d2248,0x2ed733c3,0xb3c3aed7,0xa248b26d,
  0xb3c3a248,0x315fb01d,0xa8b2333b,0xaed7b3ea,0x33ea2248,0xb388abc6,0x32dd2ed7,0xb1edb0c4,0xb2dda248,0x224832dd,0x326db33b,0xb38828b2,
  0x30c42248,0x333bb3c3,0xabc6aed7,0xb3fe326d,0xabc6a248,0xb1ed301d,0xb3ea333b,0xb33b33ea,0xb26d31ed,0xb33b32dd,0xb3c33388,0xb3fe33ea,
  0xb3c331ed,0xb1ed33c3,0x28b22d64,0x333bb0c4,0xb3ea31ed,0x2d64301d,0x32ddb388,0xb15fa8b2,0xb2dd31ed,0x33feabc6,0xb26dad64,0x2d64326d,
  0xb0c431ed,0x2ed7b2dd,0xabc63388,0x2248b3ea,0xabc631ed,0xb15fb3c3,0x33ea2d64,0xaed730c4,0x28b231ed,0xb388b01d,0xb01db388,0x31ed28b2,
  0x301d31ed,0xa2482bc6,0xb0c4ad64,0xb388b26d,0xb3ea33fe,0xb38833c3,0xb2dd333b,0xb1ed326d,0x32ddb3fe,0x2248b01d,0xb26d2ed7,0xb38833ea,
  0xb0c433fe,0x333babc6,0x2bc6b33b,0xb3fe30c4,0x2bc6b3fe,0xb1ed32dd,0x33eaaed7,0xb33ba8b2,0x28b233fe,0xad64b3c3,0x301d333b,0xb15fb26d,
  0xb01db3fe,0x33fe301d,0xb0c42ed7,0xad64b3ea,0x326d33fe,0xaed72bc6,0xb3c3b33b,0x2248b0c4,0xb3c3b3fe,0xb15fb2dd,0xa8b2aed7,0x2ed728b2,
  0x30c4b15f,0x2ed7b01d,0x2bc6ad64,0x2248a8b2,0x2bc6b15f,0xb15f2bc6,0xb3ea3388,0xaed7326d,0xa8b2b15f,0xb38832dd,0x301d2d64,0x31edb3ea,
  0xb01db15f,0xa24833c3,0x30c4b388,0xb38830c4,0xb26db15f,0x333b301d,0xb3c3ad64,0x33fe28b2,0xb3c3b15f,0x31edabc6,0x28b23388,0xb33bb26d,
  0xb3eab15f,0xad64b2dd,0x32dd2d64,0x315f33ea,0xb2ddb15f,0xb3feb3c3,0xb26db388,0xad64b0c4,0xa8b22248,0xad642bc6,0xb01d2ed7,0xb15f30c4,
  0x301da248,0x33feb2dd,0x30c4b33b,0xad64a8b2,0xb26d2248,0xaed733c3,0x33c3aed7,0x2248b26d,0x33c3a248,0xb15fb01d,0x28b2333b,0x2ed7b3ea,
  0xb3ea2248,0x3388abc6,0xb2dd2ed7,0x31edb0c4,0x32dda248,0xa24832dd,0xb26db33b,0x338828b2,0xb0c42248,0xb33bb3c3,0x2bc6aed7,0x33fe326d,
  0x2bc6a248,0x31ed301d,0x33ea333b,0x333b33ea,0x30c4315f,0x2ed7301d,0x2bc62d64,0x224828b2,0x2bc6315f,0xb15fabc6,0xb3eab388,0xaed7b26d,
  0xa8b2315f,0xb388b2dd,0x301dad64,0x31ed33ea,0xb01d315f,0xa248b3c3,0x30c43388,0xb388b0c4,0xb26d315f,0x333bb01d,0xb3c32d64,0x33fea8b2,
  0xb3c3315f,0x31ed2bc6,0x28b2b388,0xb33b326d,0xb3ea315f,0xad6432dd,0x32ddad64,0x315fb3ea,0xb2dd315f,0xb3fe33c3,0xb26d3388,0xad6430c4,
  0xa8b2a248,0xad64abc6,0xb01daed7,0xb15fb0c4,0x301d2248,0x33fe32dd,0x30c4333b,0xad6428b2,0xb26da248,0xaed7b3c3,0x33c32ed7,0x2248326d,
  0x33c32248,0xb15f301d,0x28b2b33b,0x2ed733ea,0xb3eaa248,0x33882bc6,0xb2ddaed7,0x31ed30c4,0x32dd2248,0xa248b2dd,0xb26d333b,0x3388a8b2,
  0xb0c4a248,0xb33b33c3,0x2bc62ed7,0x33feb26d,0x2bc62248,0x31edb01d,0x33eab33b,0x333bb3ea,0x326d31ed,0x333b32dd,0x33c33388,0x33fe33ea,
  0x33c331ed,0x31ed33c3,0xa8b22d64,0xb33bb0c4,0x33ea31ed,0xad64301d,0xb2ddb388,0x315fa8b2,0x32dd31ed,0xb3feabc6,0x326dad64,0xad64326d,
  0x30c431ed,0xaed7b2dd,0x2bc63388,0xa248b3ea,0x2bc631ed,0x315fb3c3,0xb3ea2d64,0x2ed730c4,0xa8b231ed,0x3388b01d,0x301db388,0xb1ed28b2,
  0xb01d31ed,0x22482bc6,0x30c4ad64,0x3388b26d,0x33ea33fe,0x338833c3,0x32dd333b,0x31ed326d,0xb2ddb3fe,0xa248b01d,0x326d2ed7,0x338833ea,
  0x30c433fe,0xb33babc6,0xabc6b33b,0x33fe30c4,0xabc6b3fe,0x31ed32dd,0xb3eaaed7,0x333ba8b2,0xa8b233fe,0x2d64b3c3,0xb01d333b,0x315fb26d,
  0x301db3fe,0xb3fe301d,0x30c42ed7,0x2d64b3ea,0xb26d33fe,0x2ed72bc6,0x33c3b33b,0xa248b0c4,0x33c3b3fe,0x315fb2dd,0x28b2aed7,0xaed728b2,
  0xb0c4315f,0xaed7301d,0xabc62d64,0xa24828b2,0xabc6315f,0x315fabc6,0x33eab388,0x2ed7b26d,0x28b2315f,0x3388b2dd,0xb01dad64,0xb1ed33ea,
  0x301d315f,0x2248b3c3,0xb0c43388,0x3388b0c4,0x326d315f,0xb33bb01d,0x33c32d64,0xb3fea8b2,0x33c3315f,0xb1ed2bc6,0xa8b2b388,0x333b326d,
  0x33ea315f,0x2d6432dd,0xb2ddad64,0xb15fb3ea,0x32dd315f,0x33fe33c3,0x326d3388,0x2d6430c4,0x28b2a248,0x2d64abc6,0x301daed7,0x315fb0c4,
  0xb01d2248,0xb3fe32dd,0xb0c4333b,0x2d6428b2,0x326da248,0x2ed7b3c3,0xb3c32ed7,0xa248326d,0xb3c32248,0x315f301d,0xa8b2b33b,0xaed733ea,
  0x33eaa248,0xb3882bc6,0x32ddaed7,0xb1ed30c4,0xb2dd2248,0x2248b2dd,0x326d333b,0xb388a8b2,0x30c4a248,0x333b33c3,0xabc62ed7,0xb3feb26d,
  0xabc62248,0xb1edb01d,0xb3eab33b,0xb33bb3ea,0xb26d31ed,0xb33b32dd,0xb3c33388,0xb3fe33ea,0xb3c331ed,0xb1ed33c3,0x28b22d64,0x333bb0c4,
  0xb3ea31ed,0x2d64301d,0x32ddb388,0xb15fa8b2,0xb2dd31ed,0x33feabc6,0xb26dad64,0x2d64326d,0xb0c431ed,0x2ed7b2dd,0xabc63388,0x2248b3ea,
  0xabc631ed,0xb15fb3c3,0x33ea2d64,0xaed730c4,0x28b231ed,0xb388b01d,0xb01db388,0x31ed28b2,0x301d31ed,0xa2482bc6,0xb0c4ad64,0xb388b26d,
  0xb3ea33fe,0xb38833c3,0xb2dd333b,0xb1ed326d,0x32ddb3fe,0x2248b01d,0xb26d2ed7,0xb38833ea,0xb0c433fe,0x333babc6,0x2bc6b33b,0xb3fe30c4,
  0x2bc6b3fe,0xb1ed32dd,0x33eaaed7,0xb33ba8b2,0x28b233fe,0xad64b3c3,0x301d333b,0xb15fb26d,0xb01db3fe,0x33fe301d,0xb0c42ed7,0xad64b3ea,
  0x326d33fe,0xaed72bc6,0xb3c3b33b,0x2248b0c4,0xb3c3b3fe,0xb15fb2dd,0xa8b2aed7,0x2ed728b2,0x29ed29ed,0x29ed29ed,0x29ed29ed,0x29ed29ed,
  0x2bc32a6d,0x2add2bea,0x23c628c4,0xa81da0b2,0x2bc32add,0xa3c6281d,0xabc3aadd,0x23c6a81d,0x29ed2b3b,0xabfea564,0x295fa6d7,0x1a482b88,
  0x25642b88,0xa564ab88,0x25642b88,0xa564ab88,0xa0b22bc3,0x2a6daadd,0xabea23c6,0x28c4281d,0xa8c42bea,0x2a6da0b2,0x28c4abea,0xaa6d20b2,
  0xab3b2bfe,0xa564295f,0x26d79a48,0x2b88a9ed,0x29ed29ed,0x29ed29ed,0x29ed29ed,0x29ed29ed,0xabc3aa6d,0xaaddabea,0xa3c6a8c4,0x281d20b2,
  0x2bc32add,0xa3c6281d,0xabc3aadd,0x23c6a81d,0xa9edab3b,0x2bfe2564,0xa95f26d7,0x9a48ab88,0x25642b88,0xa564ab88,0x25642b88,0xa564ab88,
  0x20b2abc3,0xaa6d2add,0x2beaa3c6,0xa8c4a81d,0xa8c42bea,0x2a6da0b2,0x28c4abea,0xaa6d20b2,0x2b3babfe,0x2564a95f,0xa6d71a48,0xab8829ed,
  0x295f295f,0x295f295f,0x295f295f,0x295f295f,0x23c628c4,0xa81da0b2,0xabc3aa6d,0xaaddabea,0xa3c6281d,0xabc3aadd,0x23c6a81d,0x2bc32add,
  0xa95f26d7,0x9a48ab88,0x29ed2b3b,0xabfea564,0xab882564,0x2b88a564,0xab882564,0x2b88a564,0xabea23c6,0x28c4281d,0x20b2abc3,0xaa6d2add,
  0xaa6d20b2,0xa8c42bea,0x2a6da0b2,0x28c4abea,0xa6d71a48,0xab8829ed,0xab3b2bfe,0xa564295f,0x295f295f,0x295f295f,0x295f295f,0x295f295f,
  0xa3c6a8c4,0x281d20b2,0x2bc32a6d,0x2add2bea,0xa3c6281d,0xabc3aadd,0x23c6a81d,0x2bc32add,0x295fa6d7,0x1a482b88,0xa9edab3b,0x2bfe2564,
  0xab882564,0x2b88a564,0xab882564,0x2b88a564,0x2beaa3c6,0xa8c4a81d,0xa0b22bc3,0x2a6daadd,0xaa6d20b2,0xa8c42bea,0x2a6da0b2,0x28c4abea,
  0x26d79a48,0x2b88a9ed,0x2b3babfe,0x2564a95f,0xabfe2bfe,0xabfe2bfe,0xabfe2bfe,0xabfe2bfe,0xaadd2bea,0xa3c628c4,0x281da0b2,0x2bc3aa6d,
  0xa81d2bc3,0x2adda3c6,0x281dabc3,0xaadd23c6,0x9a482b88,0x29edab3b,0xabfe2564,0x295f26d7,0x26d72b3b,0xa6d7ab3b,0x26d72b3b,0xa6d7ab3b,
  0x2a6d2add,0xabeaa3c6,0x28c4a81d,0x20b22bc3,0x2bea2a6d,0xa0b228c4,0xabeaaa6d,0x20b2a8c4,0x2b8829ed,0x2b3b2bfe,0x2564295f,0xa6d79a48,
  0xabfe2bfe,0xabfe2bfe,0xabfe2bfe,0xabfe2bfe,0x2addabea,0x23c6a8c4,0xa81d20b2,0xabc32a6d,0xa81d2bc3,0x2adda3c6,0x281dabc3,0xaadd23c6,
  0x1a48ab88,0xa9ed2b3b,0x2bfea564,0xa95fa6d7,0x26d72b3b,0xa6d7ab3b,0x26d72b3b,0xa6d7ab3b,0xaa6daadd,0x2bea23c6,0xa8c4281d,0xa0b2abc3,
  0x2bea2a6d,0xa0b228c4,0xabeaaa6d,0x20b2a8c4,0xab88a9ed,0xab3babfe,0xa564a95f,0x26d71a48,0x1a489a48,0x1a489a48,0x1a489a48,0x1a489a48,
  0x281da0b2,0x2bc3aa6d,0x2addabea,0x23c6a8c4,0x2adda3c6,0x281dabc3,0xaadd23c6,0xa81d2bc3,0x2bfea564,0xa95fa6d7,0x9a482b88,0x29edab3b,
  0x2b3ba6d7,0xab3b26d7,0x2b3ba6d7,0xab3b26d7,0x28c4a81d,0x20b22bc3,0xaa6daadd,0x2bea23c6,0x20b2a8c4,0x2bea2a6d,0xa0b228c4,0xabeaaa6d,
  0xa564a95f,0x26d71a48,0x2b8829ed,0x2b3b2bfe,0x1a489a48,0x1a489a48,0x1a489a48,0x1a489a48,0xa81d20b2,0xabc32a6d,0xaadd2bea,0xa3c628c4,
  0x2adda3c6,0x281dabc3,0xaadd23c6,0xa81d2bc3,0xabfe2564,0x295f26d7,0x1a48ab88,0xa9ed2b3b,0x2b3ba6d7,0xab3b26d7,0x2b3ba6d7,0xab3b26d7,
  0xa8c4281d,0xa0b2abc3,0x2a6d2add,0xabeaa3c6,0x20b2a8c4,0x2bea2a6d,0xa0b228c4,0xabeaaa6d,0x2564295f,0xa6d79a48,0xab88a9ed,0xab3babfe,
  0xa95fa95f,0xa95fa95f,0xa95fa95f,0xa95fa95f,0xa3c6a8c4,0x281d20b2,0x2bc32a6d,0x2add2bea,0x23c6a81d,0x2bc32add,0xa3c6281d,0xabc3aadd,
  0x295fa6d7,0x1a482b88,0xa9edab3b,0x2bfe2564,0x2b88a564,0xab882564,0x2b88a564,0xab882564,0x2beaa3c6,0xa8c4a81d,0xa0b22bc3,0x2a6daadd,
  0x2a6da0b2,0x28c4abea,0xaa6d20b2,0xa8c42bea,0x26d79a48,0x2b88a9ed,0x2b3babfe,0x2564a95f,0xa95fa95f,0xa95fa95f,0xa95fa95f,0xa95fa95f,
  0x23c628c4,0xa81da0b2,0xabc3aa6d,0xaaddabea,0x23c6a81d,0x2bc32add,0xa3c6281d,0xabc3aadd,0xa95f26d7,0x9a48ab88,0x29ed2b3b,0xabfea564,
  0x2b88a564,0xab882564,0x2b88a564,0xab882564,0xabea23c6,0x28c4281d,0x20b2abc3,0xaa6d2add,0x2a6da0b2,0x28c4abea,0xaa6d20b2,0xa8c42bea,
  0xa6d71a48,0xab8829ed,0xab3b2bfe,0xa564295f,0x29ed29ed,0x29ed29ed,0x29ed29ed,0x29ed29ed,0x2bc32a6d,0x2add2bea,0x23c628c4,0xa81da0b2,
  0x2bc32add,0xa3c6281d,0xabc3aadd,0x23c6a81d,0x29ed2b3b,0xabfea564,0x295fa6d7,0x1a482b88,0x25642b88,0xa564ab88,0x25642b88,0xa564ab88,
  0xa0b22bc3,0x2a6daadd,0xabea23c6,0x28c4281d,0xa8c42bea,0x2a6da0b2,0x28c4abea,0xaa6d20b2,0xab3b2bfe,0xa564295f,0x26d79a48,0x2b88a9ed,
  0x29ed29ed,0x29ed29ed,0x29ed29ed,0x29ed29ed,0xabc3aa6d,0xaaddabea,0xa3c6a8c4,0x281d20b2,0x2bc32add,0xa3c6281d,0xabc3aadd,0x23c6a81d,
  0xa9edab3b,0x2bfe2564,0xa95f26d7,0x9a48ab88,0x25642b88,0xa564ab88,0x25642b88,0xa564ab88,0x20b2abc3,0xaa6d2add,0x2beaa3c6,0xa8c4a81d,
  0xa8c42bea,0x2a6da0b2,0x28c4abea,0xaa6d20b2,0x2b3babfe,0x2564a95f,0xa6d71a48,0xab8829ed,0x9a481a48,0x9a481a48,0x9a481a48,0x9a481a48,
  0xa81d20b2,0xabc32a6d,0xaadd2bea,0xa3c628c4,0xaadd23c6,0xa81d2bc3,0x2adda3c6,0x281dabc3,0xabfe2564,0x295f26d7,0x1a48ab88,0xa9ed2b3b,
  0xab3b26d7,0x2b3ba6d7,0xab3b26d7,0x2b3ba6d7,0xa8c4281d,0xa0b2abc3,0x2a6d2add,0xabeaa3c6,0xa0b228c4,0xabeaaa6d,0x20b2a8c4,0x2bea2a6d,
  0x2564295f,0xa6d79a48,0xab88a9ed,0xab3babfe,0x9a481a48,0x9a481a48,0x9a481a48,0x9a481a48,0x281da0b2,0x2bc3aa6d,0x2addabea,0x23c6a8c4,
  0xaadd23c6,0xa81d2bc3,0x2adda3c6,0x281dabc3,0x2bfea564,0xa95fa6d7,0x9a482b88,0x29edab3b,0xab3b26d7,0x2b3ba6d7,0xab3b26d7,0x2b3ba6d7,
  0x28c4a81d,0x20b22bc3,0xaa6daadd,0x2bea23c6,0xa0b228c4,0xabeaaa6d,0x20b2a8c4,0x2bea2a6d,0xa564a95f,0x26d71a48,0x2b8829ed,0x2b3b2bfe,
  0xabfe2bfe,0xabfe2bfe,0xabfe2bfe,0xabfe2bfe,0xaadd2bea,0xa3c628c4,0x281da0b2,0x2bc3aa6d,0xa81d2bc3,0x2adda3c6,0x281dabc3,0xaadd23c6,
  0x9a482b88,0x29edab3b,0xabfe2564,0x295f26d7,0x26d72b3b,0xa6d7ab3b,0x26d72b3b,0xa6d7ab3b,0x2a6d2add,0xabeaa3c6,0x28c4a81d,0x20b22bc3,
  0x2bea2a6d,0xa0b228c4,0xabeaaa6d,0x20b2a8c4,0x2b8829ed,0x2b3b2bfe,0x2564295f,0xa6d79a48,0xabfe2bfe,0xabfe2bfe,0xabfe2bfe,0xabfe2bfe,
  0x2addabea,0x23c6a8c4,0xa81d20b2,0xabc32a6d,0xa81d2bc3,0x2adda3c6,0x281dabc3,0xaadd23c6,0x1a48ab88,0xa9ed2b3b,0x2bfea564,0xa95fa6d7,
  0x26d72b3b,0xa6d7ab3b,0x26d72b3b,0xa6d7ab3b,0xaa6daadd,0x2bea23c6,0xa8c4281d,0xa0b2abc3,0x2bea2a6d,0xa0b228c4,0xabeaaa6d,0x20b2a8c4,
  0xab88a9ed,0xab3babfe,0xa564a95f,0x26d71a48,0x3bfb3bff,0x3be53bf2,0x3bbf3bd4,0x3b873ba5,0x3bd03bfb,0x3b013b7c,0x399d3a60,0x378538bc,
  0x35173b52,0xbbc9b7c8,0xb074ba9b,0x3bfe391b,0x319e3b27,0xbbf3b979,0x363cb80a,0x3a2d3bc5,0xba093986,0x3a7eb8f8,0xbae5385f,0x3b3db77a,
  0xbabd393c,0x3bb0b699,0xbc00305b,0x3ba730d7,0xbb2a35c8,0xb8353bb2,0x3a64b1e8,0x3962bbf7,0xba90350b,0xba413bff,0x3602340e,0x3bf6bad8,
  0xac6aa5e4,0xb122af59,0xb402b294,0xb56ab4b7,0xb2deac9c,0xb7bdb5a5,0xb9b3b8d6,0xbb10ba73,0xbb96b676,0xb359bafe,0x3bec3884,0x2a163a29,
  0xbbe0b72c,0x2f27b9d6,0x3b5e3ae8,0xb91633a2,0xb941b9c9,0x38ad3a45,0xb80fbab3,0x36d23b13,0xb850ba0d,0x346f3b4a,0x1fdbbbed,0xb4ab3be8,
  0x3721bb76,0xbace3463,0xb8d13bdd,0x39ebadfb,0x3894bb98,0xb8fd281f,0xbb6a3bbd,0x2e2d3825,0x3b3f3b65,0x3ae83b16,0x3a813ab6,0x3a0d3a49,
  0x3263356a,0xad972b43,0xb5dfb359,0xb8eeb7f3,0xa9b139aa,0xbbedba25,0x3340b889,0x3b983afb,0xbaa2aa16,0xb4cfbb8e,0x3c0038ad,0xb44b38e5,
  0xbb853625,0x3bbdb4c3,0xbbe432ad,0x3bfbaf8b,0xbaacb6d2,0x39243954,0xb65fbace,0x2fbd3bb8,0xb9661648,0xba603bf8,0x383a31cf,0x3b27bbb3,
  0x3219b9eb,0xbb1836f4,0xb9903be5,0x37dd3010,0xb6c6b61a,0xb80ab76f,0xb8a8b85a,0xb93cb8f3,0xbbd7bb87,0xbbf8bbfd,0xbb71bbc9,0xba4dbaf1,
  0xbbfeb9a6,0x305bb91f,0x3bcb3a97,0xb50b37d2,0xb87abbfe,0x3ba13546,0x24523a7e,0xbbb5ba54,0xb576bb63,0x340e3ba3,0xb13bbbd3,0x2c9c3bf2,
  0x386abb3d,0xba2139f8,0x3b57b835,0xbbf13432,0x39e7bc00,0xb8d6adc9,0xbacb3bde,0x372c3457,0x3bdab962,0x3764bb35,0xb9c03122,0xbaf73bef,
  0x398b39cd,0x38fd3946,0x386538b2,0x37853815,0xba85b9c9,0xbb92bb1e,0xbbfebbdd,0xbbc2bbf5,0xb66b3682,0xbb01bb94,0x387fb371,0x3a2d3beb,
  0xbac7bb76,0x3a00ad33,0x36bb3bd4,0xbbeab79b,0xbc0026ad,0x3bf32c38,0xbbd6b109,0x3ba733eb,0x3153bbff,0xb70a3b9e,0x396bba9b,0xbade390c,
  0xb5d4b5bc,0xbbb03b2c,0x32013830,0x3bf6ba67,0x3bccbb52,0x2c06b92e,0xbb83385f,0xb8c73bab,0xb9c5b982,0xba41ba04,0xbab0ba7a,0xbb10bae1,
  0xb8a3b986,0xb52fb74e,0xa94db1e8,0x33d32e91,0xbb54bb4f,0x37bdb523,0x3a9e3bc8,0xb916308d,0x3840b5c8,0x394a3bf9,0xbb42b294,0xb0a6bb0a,
  0x251bbbff,0xaf273bfc,0x327cbbe6,0xb4ab3bc0,0x3be325e4,0xbb2fb4e7,0x39e33884,0xb81aba35,0x3b73bb78,0xb46fb715,0xbbdc3ad1,0x2e2d38cc,
  0x33283676,0x3bfcba19,0x3581bab3,0xba6b3493,0x363136dd,0x34cf3581,0x32c6341a,0x2fbd3153,0xbae1bb65,0xb970ba39,0xb715b889,0xb16cb4f3,
  0xb9a12a7a,0xb924bbfe,0x3a933042,0x37dd3bcc,0x308db9aa,0x3b453b07,0xb94632ad,0xb845bbfa,0xbb68b55e,0x3b1836bb,0xbabab805,0x3a4d38a3,
  0x3bc0b625,0xbbfe2ec3,0x3b9431cf,0xba89b742,0x9cb6b95d,0xbbf8396b,0xb1b63a5c,0x3bb5b840,0x38cc9648,0x3b81bbac,0xac38b85a,0xbbce3933,
  0xbb60bb3a,0xbba1bb83,0xbbd2bbbc,0xbbf1bbe3,0x3815361a,0x39df3907,0x3b2c3a97,0x3be23b9c,0xb9afbbfd,0x3a21294d,0x388e3bee,0xbaf7b328,
  0x3beb39a6,0xb6af37a6,0xba04bbd3,0x3ac42d00,0x360ebb89,0xb7643b42,0x3855baeb,0xb8ee3a85,0x33eb3b63,0x28e8bbf5,0xb5233bde,0x389ebb21,
  0x3c00b9f0,0x2d97b9e3,0xbbdf38db,0xb44b3ac7,0xba673c00,0x358d3487,0x3bfcbab6,0x330fba15,0x3b7a3bf1,0x394a3a93,0x33893764,0xb3d39cb6,
  0x3afb3be2,0x35eb3946,0xb4c328e8,0xbaa9b8cc,0x27763af7,0xbb2fbaba,0x3a76ad97,0x30a63b60,0xaf8b3ac4,0xb994bb94,0x3bf8358d,0xb8743815,
  0xbb4c38ee,0x3bfcb1b6,0xbad5b4cf,0x381a39af,0xbbb3389e,0x3b592c38,0xb76fb970,0xb24b3beb,0xb9d2344b,0xbb923bd2,0xb0f03924,0x3a6bb60e,
  0xb8f3330f,0xbc003b2c,0xb91f3b45,0x323233eb,0xb5b1afbd,0xba00b88e,0xbbc6bb18,0xbbc2bc00,0xb7d2b16c,0xbb6fba04,0xbba3bbfe,0xb86fba67,
  0xbbffb7dd,0x370ab855,0x38b73bf8,0xbbeab631,0xbbf2b845,0x39bcb523,0x2dc93b81,0xbaa5bae1,0xb68dba4d,0xac063bdf,0x382abba1,0xbade39a1,
  0xb457ba89,0xb6543bfc,0x3b16b9df,0xbbd8308d,0x397dbbb5,0xb52fb2c6,0xbbe73a21,0xb8c73b68,0x3a49bbce,0x2311b715,0xba2536af,0xbbd93bc0,
  0xb958b785,0xbb81ba9e,0xbbefbbf3,0xba89bb73,0xbbf7bbc2,0xb9b8bb42,0xaf59b70a,0x384a3328,0xbb8bba2d,0x39dfb27c,0x34263bb0,0xbbceb98b,
  0xb4b7bbea,0x3b6c39e3,0xbafe2c06,0x3185ba85,0xaadebba7,0xb6af3bdc,0x3a58ba41,0xbbe2366b,0x3a29bade,0xbc003581,0x3a45352f,0xb2f7bac7,
  0x3b37bbf6,0x28e8b865,0xbaee37bd,0xbac43c00,0x3b13b8c7,0x3b5cbbfe,0x3463b94a,0xb8993153,0xb9f4bb10,0xb58db87f,0x3029af27,0x389e35d4,
  0x2dfbb3d3,0x399936bb,0x3bf23b2f,0x3ac13bcc,0x3552b916,0x39703bd6,0xbbbab46f,0x330fb9c5,0x3ba530a6,0xb5f7396b,0xb7c8bbfc,0x3be138a3,
  0x3bfdb4ab,0xbb45b201,0x38e038fd,0xb16cbb54,0x391b381a,0xa17fbb83,0xb8f83b92,0x3bcfb840,0x36e82e2d,0x3bfebab0,0x37febb01,0xb845251b,
  0xb77a3a6b,0x3648294d,0x3bb2ba00,0x3a8cbbe3,0xb742b93c,0x2311b340,0x37a6340e,0x3aa93966,0x3b963a4d,0x3b7f3c00,0x380f3a21,0xb0be3219,
  0x3933b50b,0x35eb3be4,0xbbf5b8d6,0x3874b6c6,0x39413bb5,0xbbffb65f,0x38d1b764,0x33ba3bd7,0x3b9c2c9c,0xb994b83a,0x34873ae8,0x324bbbfe,
  0xb7213bf1,0x3b47b990,0xbbbf2d97,0x38c1387a,0x2d00372c,0x3b59b8a8,0x3a39bbed,0xb232b576,0xbbfb3af7,0xb9743b71,0x307434cf,0x3adbb86a,
  0x3b213a0d,0x3c003bcb,0x3b073bbd,0x386f39e7,0x351738ee,0xb599a452,0xbae5b924,0xbbe9bbda,0x3a153b98,0xbb6fb13b,0x2ec3ba60,0x3aa53b3f,
  0xba09344b,0xa884bb57,0x3a643b18,0xbbc3b263,0xb4f33bfb,0x39bcbacb,0xbbac380a,0x3bd8a9b1,0xbb2aafbd,0x36a439c0,0x3402bbf8,0xba6f3aa2,
  0xbbfa3b27,0xb6543a81,0x3907b05b,0x3bd9bb85,0x2c6ab7dd,0xb9da35df,0xbbec3ba1,0xb8203aac,0x3bf53b87,0x3b6c3bec,0x392e3a7e,0x32f73721,
  0xb9e7b785,0xbbfcbb5e,0xba81bbb0,0xb43eb894,0x379b3bfe,0xbc00b80f,0x374eb835,0x38993bfb,0xbb3fba2d,0x3b329fdb,0xb3403a41,0xb8eabbd0,
  0xb90c3b3d,0x3b5cb8d1,0xbbf93122,0x3ac13517,0x29b1bba7,0xb94f3b6a,0x3be4b7bd,0xbaf4b19e,0xbbab3962,0xb9993bbf,0x34e73359,0x3be1ba09,
  0x3b85bbf6,0x353ab99d,0xb83a2f27,0xbbf03abd,0x2e91356a,0xb5f7b074,0xba19b8ad,0xbbcfbb2a,0xb966bb10,0xaba7b63c,0x38a8346f,0x3bb73a90,
  0xbb0aaa16,0xa17fbae5,0x3b1e3ace,0xba8c2c6a,0x36c6b916,0x36ff3c00,0xbbcbb8fd,0x3a50b2de,0xba35b6d2,0x36483a64,0x2d33bbe5,0xb84a3b96,
  0x3bfeb4ab,0xb9fcb602,0x313b3b01,0x37e8bbe0,0x3493b9eb,0xb9b83402,0xbb9e3bc9,0xb1853941,0x35762e2d,0x3b90b9b3,0x3acbbbf3,0x2fefb850,
  0x3a543bcf,0x2884374e,0xb9f8b648,0xbbe9bbab,0x398b3bb7,0xb4db3340,0xbbdcb9fc,0xb911bb85,0xb4323a8c,0xb6a4bbf9,0x3b3539b8,0xbbc3ae91,
  0xb66b3a50,0xad65bbe4,0x38653b90,0xbb0db966,0xbbef384a,0x39da34e7,0x2b43bb6c,0xba6f3b0a,0xbc0037e8,0x3759383a,0x387fbbfc,0xbbf636c6,
  0xb7f33185,0xbb7f3a19,0xbb8e3c00,0xb8203a35,0xb5d42fef,0xba1d38a8,0xbbd63b32,0xbba93bfe,0xb8e5b2f7,0xbbffbb1e,0xb954bb5c,0x30beb493,
  0xb9c5b43e,0xbb9fbbcb,0xb201b94f,0x3a313576,0xbbb8b899,0x3b47ad33,0xb6f43999,0xb3babbf5,0xbb54b8ea,0x3bf9313b,0xbab0353a,0x3790b9e7,
  0xb010bac1,0xb9743b9e,0x3bfdb5f7,0xb8c1b79b,0x251bbaf4,0xbb1b3acb,0x3a9e2ba7,0x2e5fbb3f,0x3af1bbe1,0x3599b92e,0xb546a17f,0xbadb390c,
  0x3b73bbf0,0x3929ba81,0x327cb6ff,0xb49f29b1,0xb825baa9,0x353aaec3,0x3b7c3994,0x3af43bfa,0x360eb0be,0x3bf43a64,0x388e3b47,0xb7372c6a,
  0x38bcb874,0x2ba73bac,0xb979bb59,0x3bf03742,0x3c0033ba,0xbb043402,0x3855b974,0xacce3b96,0x3bc5b24b,0xb6ffb907,0xb6993c00,0x3bb7b933,
  0x363138c1,0x3902bbec,0xbbdf3599,0x34ff3941,0x30d73232,0x39fcb7a6,0x3bffbb6f,0x3a50bb9c,0xb9a13adb,0xb47b380f,0x32c62884,0x3937b721,
  0x3ad8386f,0x3b903bf5,0x35a539bc,0xb7e8ad00,0x3b683be9,0x2ef538d1,0xba93b6a4,0xbb24bbfb,0x3a733aa5,0xbbfcb487,0x39d6b654,0xafef3b21,
  0x1cb63bc3,0xb7b2bbbf,0x3aba39da,0xbbfab517,0xb3a23bd8,0x3b32ba39,0xbb4a2311,0x343e3a15,0xbb603a6f,0x3a3d3074,0x31b6bb7f,0xbb9a3a09,
  0xbbe83bd9,0xb94f3b07,0xa81f35eb,0x38eab4f3,0xb9af3820,0xbbae3ae5,0xbbd23bff,0xba113b2a,0x319e389e,0xb929b426,0xbc00bb45,0xb911bb37,
  0xbbffbac1,0xb805bafe,0x382a217f,0x3bfd3b13,0xbabd330f,0x34dbba58,0x36023bfe,0xbb0db9f4,0xb68dbbe1,0x3a5c3a45,0xbbe7b648,0x3b89adfb,
  0xba90b16c,0x2d653aee,0x39b3bb81,0xbbf63552,0x397dbbcf,0xbbbc3463,0x338939b8,0x39f0bba5,0x32deb845,0xb7593029,0xbb5e39df,0xbba93bfd,
  0x3b7aba8c,0x3beebbf2,0x3a76bb6c,0x36ddb91b,0xbbe0ba89,0xba1dbbba,0x1fdbb6af,0x3a3136e8,0xa776b84a,0x3aeb37c8,0x3ad53c00,0xaa7a377a,
  0xb850bbce,0x3b9f38e0,0xbb6a28e8,0x3790b958,0x3b4cb185,0xb8db38f8,0x30f0bb5c,0x355e3bf7,0x3894bbe2,0xbbf937fe,0x399d358d,0x2e5fbb8b,
  0x39d232f7,0x341abbb2,0xbbc63999,0x395d34b7,0x3bd0bac4,0x3b1bbbef,0x363cb970,0xb49faade,0xb5b13899,0x30422f59,0x38b7b5f7,0x3b3aba29,
  0x3219b3d3,0x3b0438b7,0x3b713bfc,0x34ff397d,0x36e83aa9,0xb8b2adc9,0xbbefbb59,0xb5bcba49,0x3bd730a6,0xb902382a,0xa452bb92,0x39373b7a,
  0xb9583874,0x3371bb16,0x34263c00,0xb982bafb,0x387a381a,0x347bbbe7,0xbb573a00,0x3b242776,0xbb8b324b,0x31093a25,0x3a58bb6f,0xbb4f2f8b,
  0xb86a3a6b,0x2ef53389,0x39c0b70a,0x3bfabb4c,0xaadeb232,0xb83034c3,0xbaee39bc,0xbbff3bb3,0x3bda3bc2,0x37b23a76,0xb5df2c06,0xbb9ab9d2,
  0xbb37b86f,0xba7abbf8,0x3029b654,0x3b7838f3,0x32633bea,0xba3dbad5,0x3c00352f,0xba1135b1,0xb9f4baa5,0x3bc8376f,0xbbba2311,0x39cdb7d2,
  0xbaa23ade,0x3baeb0f0,0xb65fb94a,0xb7373bff,0x3552bbd8,0xbbe6391f,0x38e035eb,0x3682bbf2,0xbaac38c7,0xbbf43bc6,0xb9903b2f,0xacce368d,
  0x3bfdbbd9,0x3ad1bba3,0x37feb994,0x26adb457,0x38a33b9a,0xb8dba452,0xbb83bbae,0x2a7ab86a,0x37423b78,0xbab6b426,0xb907bbe6,0x39aa2ade,
  0xb8403a11,0x341abb57,0x294d3bf4,0xb55ebbda,0xb93339cd,0x3889ba58,0xb7a63ad1,0x3625bb37,0xbbe33737,0x304239c0,0x3b42bb04,0xb95db263,
  0xbb9c3682,0xb2ad3aee,0x3bf5b8b2,0x1648b9f4,0xb3282cce,0xb80535df,0xb9e33902,0xbb3a3aa2,0xad0026ad,0xb1cf3029,0xb4873371,0xb61a3552,
  0xba85b4ff,0xba5cbc00,0x3581b47b,0x3bfd3aac,0xbb21b5bc,0xb85abbba,0x3a393109,0x39a63bfd,0xbac7b937,0x3bbc365f,0xbbfeaef5,0x3b89b219,
  0xba15b982,0x3a9738e0,0xbb07b830,0x3b6336e8,0x3153bb24,0xbbee3990,0x36bb37b2,0x39f0bbd7,0x34f3bb4f,0xbbd337fe,0xaec33a7a,0x3c00b958,
  0x3bccbbfa,0x3aebbb71,0x396bba3d,0x36ddb87a,0x3bfabbff,0x3bdebbef,0x3bacbbc8,0x3b65bb8b,0x3bc03911,0x38303b6a,0xb946ad65,0xbb4fbbd0,
  0x3a353bfd,0xb85f30f0,0xbb1ebbbc,0x35c8b5b1,0x38cc3b0d,0xba7ab99d,0x3b943759,0xbbffb19e,0xb4933b89,0x31e8bbc6,0xad333bee,0xa5e4bbff,
  0xb8153bf6,0x3bc8b63c,0xac38ba1d,0xbb783abd,0xbbf539f0,0x329438b7,0x3b9ebaeb,0xb676b68d,0xbbeb3ba9,0xbbe63c00,0xbb2c3b9f,0xb9cd3a90,
  0xb79b36dd,0xb884382a,0xb92e38db,0xb9c9397d,0x33eb3a31,0xbad1b602,0xba04bbf9,0x3682b2de,0xb90c2a7a,0xbab3bbe7,0x374eb41a,0x3b763b7a,
  0xba673790,0x38b2b9b3,0xb5233b1b,0x26adbbe0,0xbbabb55e,0x3bdd3389,0xbbf9b042,0x3bff2776,0xbae12e5f,0xb3713b5e,0x3bfcb929,0xb5bcb850,
  0xae91b95d,0xbbd43a76,0x34e73805,0x3b52bb4c,0x308db49f,0xb1091fdb,0xb71534db,0xb9823894,0x3b0abb3a,0x3a9bbad5,0x3a19ba5c,0x3986b9d2,
  0x2f8bb7e8,0x3bde3979,0x376f3b32,0xb9aab0d7,0x3bb83b24,0xb1223855,0xbbfdba3d,0xaa16b9a1,0x3bb3afef,0xbab63699,0x391fb94f,0xb6253ad8,
  0x30103bfa,0xb359bbdf,0x35463bae,0xb6d2bb68,0x38f3343e,0x3889bbff,0xbba3353a,0x96483a73,0xbaf13b9a,0x38ad32c6,0x39f8bbf4,0xb9eb9cb6,
  0xb7d238ea,0xb2ad35a5,0x2dc92ba7,0x361ab3a2,0xba543a11,0xbace3a93,0xbb353b04,0xbb873b60,0x3bf23af4,0x31cf39d6,0xbb16b6ff,0xb9a6bbe8,
  0xb4323737,0xbbe5baba,0x2b43b902,0x3bfe39af,0x34573bf0,0xb85abb4a,0x3a2539fc,0xbb63b825,0xbbef2cce,0x3bc9b1b6,0xbb8e347b,0x3b3db60e,
  0xba493bb7,0x3a97a81f,0x34c3bb90,0xbc0038bc,0xb7f3b4ff,0xba7e3bd2,0x39542ef5,0x3962bc00,0xbafb3a50,0xbbd33b7c,0xbbf83bfc,0xbb653bc5,
  0x38e5b937,0x3835b88e,0x36f4b7b2,0x356ab631,0xbb13bbe9,0x31e8b6f4,0x3bf239da,0x36763af1,0x3be83911,0x340e3ab0,0xbb7cb759,0xb72cbb73,
  0x2dfbbbc3,0x32943bfd,0xb7c8bb7f,0x39c93a54,0x38253b0d,0xb8d6ba9e,0x39793a1d,0xba0db98b,0x3ba5ba6f,0xb884b546,0xb8f83bff,0x3b76b432,
  0xb8bc3bf6,0x3ae8b27c,0x3699bb9f,0xbb98366b,0x391bb820,0x3ab3b9f8,0x3bb2bb47,0x3bffbbef,0xbbc53ba9,0xbbed3bdc,0xbbff3bf9,0xbbfb3c00,
  0x377ab0be,0x3bdd3b35,0x2f593974,0xbb52b7f3,0x30d73a31,0xbbbdb865,0xb5a5bb1b,0x3b2735d4,0x3bf733ba,0xbbd42b43,0x3afeb599,0xb98638e5,
  0xbad83790,0x3a60b87f,0xb9d63929,0x393cb9c5,0x34b738c1,0x3a9bbb8e,0xba45a884,0xb5c83bb8,0xba732e5f,0xb80a3bd6,0x3b4ab4db,0x350bbb54,
  0xba293adb,0xb85f3954,0xb46336a4,0x25e43010,0x33a2b49f,0x305bb201,0x281fad65,0xac9c251b,0x3f803f80,0x3f803f80,0x3f803f80,0x3f803f80,
  0x3f803f80,0x3f803f80,0x3f803f80,0x3f803f80,0x3f803f80,0x3f803f80,0x3f803f80,0x3f803f80,0x3f803f80,0x3f803f80,0x3f803f80,0x3f803f80,
  0x3f803f80,0x3f803f80,0x3f803f80,0x3f803f80,0x3f803f80,0x3f803f80,0x3f803f80,0x3f803f80,0x3f803f80,0x3f803f80,0x3f803f80,0x3f803f80,
  0x3f803f80,0x3f803f80,0x3f803f80,0x3f803f80,0x3f803f80,0x3f803f80,0x3f803f80,0x3f803f80,0x3f803f80,0x3f803f80,0x3f803f80,0x3f803f80,
  0x3f803f80,0x3f803f80,0x3f803f80,0x3f803f80,0x3f803f80,0x3f803f80,0x3f803f80,0x3f803f80,0x3f803f80,0x3f803f80,0x3f803f80,0x3f803f80,
  0x3f803f80,0x3f803f80,0x3f803f80,0x3f803f80,0x3f803f80,0x3f803f80,0x3f803f80,0x3f803f80,0x3f803f80,0x3f803f80,0x3f803f80,0x3f803f80,
  0x3f803f80,0x3f803f80,0x3f803f80,0x3f803f80,0x3f803f80,0x3f803f80,0x3f803f80,0x3f803f80,0x3f803f80,0x3f803f80,0x3f803f80,0x3f803f80,
  0x3f803f80,0x3f803f80,0x3f803f80,0x3f803f80,0x3f803f80,0x3f803f80,0x3f803f80,0x3f803f80,0x3f803f80,0x3f803f80,0x3f803f80,0x3f803f80,
  0x3f803f80,0x3f803f80,0x3f803f80,0x3f803f80,0x3f803f80,0x3f803f80,0x3f803f80,0x3f803f80,0x3f803f80,0x3f803f80,0x3f803f80,0x3f803f80,
  0x3f803f80,0x3f803f80,0x3f803f80,0x3f803f80,0x3f803f80,0x3f803f80,0x3f803f80,0x3f803f80,0x3f803f80,0x3f803f80,0x3f803f80,0x3f803f80,
  0x3f803f80,0x3f803f80,0x3f803f80,0x3f803f80,0x3f803f80,0x3f803f80,0x3f803f80,0x3f803f80,0x3f803f80,0x3f803f80,0x3f803f80,0x3f803f80,
  0x3f803f80,0x3f803f80,0x3f803f80,0x3f803f80,0x3f803f80,0x3f803f80,0x3f803f80,0x3f803f80,0x3f803f80,0x3f803f80,0x3f803f80,0x3f803f80,
  0x3f803f80,0x3f803f80,0x3f803f80,0x3f803f80,0x3f803f80,0x3f803f80,0x3f803f80,0x3f803f80,0x3f803f80,0x3f803f80,0x3f803f80,0x3f803f80,
  0x3f803f80,0x3f803f80,0x3f803f80,0x3f803f80,0x3f803f80,0x3f803f80,0x3f803f80,0x3f803f80,0x3f803f80,0x3f803f80,0x3f803f80,0x3f803f80,
  0x3f803f80,0x3f803f80,0x3f803f80,0x3f803f80,0x3f803f80,0x3f803f80,0x3f803f80,0x3f803f80,0x3f803f80,0x3f803f80,0x3f803f80,0x3f803f80,
  0x3f803f80,0x3f803f80,0x3f803f80,0x3f803f80,0x3f803f80,0x3f803f80,0x3f803f80,0x3f803f80,0x3f803f80,0x3f803f80,0x3f803f80,0x3f803f80,
  0x3f803f80,0x3f803f80,0x3f803f80,0x3f803f80,0x3f803f80,0x3f803f80,0x3f803f80,0x3f803f80,0x3f803f80,0x3f803f80,0x3f803f80,0x3f803f80,
  0x3f803f80,0x3f803f80,0x3f803f80,0x3f803f80,0x3f803f80,0x3f803f80,0x3f803f80,0x3f803f80,0x3f803f80,0x3f803f80,0x3f803f80,0x3f803f80,
  0x3f803f80,0x3f803f80,0x3f803f80,0x3f803f80,0x3f803f80,0x3f803f80,0x3f803f80,0x3f803f80,0x3f803f80,0x3f803f80,0x3f803f80,0x3f803f80,
  0x3f803f80,0x3f803f80,0x3f803f80,0x3f803f80,0x3f803f80,0x3f803f80,0x3f803f80,0x3f803f80,0x3f803f80,0x3f803f80,0x3f803f80,0x3f803f80,
  0x3f803f80,0x3f803f80,0x3f803f80,0x3f803f80,0x3f803f80,0x3f803f80,0x3f803f80,0x3f803f80,0x3f803f80,0x3f803f80,0x3f803f80,0x3f803f80,
  0x3f803f80,0x3f803f80,0x3f803f80,0x3f803f80,0x3f803f80,0x3f803f80,0x3f803f80,0x3f803f80,0x3f803f80,0x3f803f80,0x3f803f80,0x3f803f80,
  0x3f803f80,0x3f803f80,0x3f803f80,0x3f803f80,0x3f803f80,0x3f803f80,0x3f803f80,0x3f803f80,0x3f803f80,0x3f803f80,0x3f803f80,0x3f803f80,
  0x3f803f80,0x3f803f80,0x3f803f80,0x3f803f80,0x3f803f80,0x3f803f80,0x3f803f80,0x3f803f80,0x3f803f80,0x3f803f80,0x3f803f80,0x3f803f80,
  0x3f803f80,0x3f803f80,0x3f803f80,0x3f803f80,0x3f803f80,0x3f803f80,0x3f803f80,0x3f803f80,0x3f803f80,0x3f803f80,0x3f803f80,0x3f803f80,
  0x3f803f80,0x3f803f80,0x3f803f80,0x3f803f80,0x3f803f80,0x3f803f80,0x3f803f80,0x3f803f80,0x3f803f80,0x3f803f80,0x3f803f80,0x3f803f80,
  0x3f803f80,0x3f803f80,0x3f803f80,0x3f803f80,0x3f803f80,0x3f803f80,0x3f803f80,0x3f803f80,0x3f803f80,0x3f803f80,0x3f803f80,0x3f803f80,
  0x3f803f80,0x3f803f80,0x3f803f80,0x3f803f80,0x3f803f80,0x3f803f80,0x3f803f80,0x3f803f80,0x3f803f80,0x3f803f80,0x3f803f80,0x3f803f80,
  0x3f803f80,0x3f803f80,0x3f803f80,0x3f803f80,0x3f803f80,0x3f803f80,0x3f803f80,0x3f803f80,0x3f803f80,0x3f803f80,0x3f803f80,0x3f803f80,
  0x3f803f80,0x3f803f80,0x3f803f80,0x3f803f80,0x3f803f80,0x3f803f80,0x3f803f80,0x3f803f80,0x3f803f80,0x3f803f80,0x3f803f80,0x3f803f80,
  0x3f803f80,0x3f803f80,0x3f803f80,0x3f803f80,0x3f803f80,0x3f803f80,0x3f803f80,0x3f803f80,0x3f803f80,0x3f803f80,0x3f803f80,0x3f803f80,
  0x3f803f80,0x3f803f80,0x3f803f80,0x3f803f80,0x3f803f80,0x3f803f80,0x3f803f80,0x3f803f80,0x3f803f80,0x3f803f80,0x3f803f80,0x3f803f80,
  0x3f803f80,0x3f803f80,0x3f803f80,0x3f803f80,0x3f803f80,0x3f803f80,0x3f803f80,0x3f803f80,0x3f803f80,0x3f803f80,0x3f803f80,0x3f803f80,
  0x3f803f80,0x3f803f80,0x3f803f80,0x3f803f80,0x3f803f80,0x3f803f80,0x3f803f80,0x3f803f80,0x3f803f80,0x3f803f80,0x3f803f80,0x3f803f80,
  0x3f803f80,0x3f803f80,0x3f803f80,0x3f803f80,0x3f803f80,0x3f803f80,0x3f803f80,0x3f803f80,0x3f803f80,0x3f803f80,0x3f803f80,0x3f803f80,
  0x3f803f80,0x3f803f80,0x3f803f80,0x3f803f80,0x3f803f80,0x3f803f80,0x3f803f80,0x3f803f80,0x3f803f80,0x3f803f80,0x3f803f80,0x3f803f80,
  0x3f803f80,0x3f803f80,0x3f803f80,0x3f803f80,0x3f803f80,0x3f803f80,0x3f803f80,0x3f803f80,0x3f803f80,0x3f803f80,0x3f803f80,0x3f803f80,
  0x3f803f80,0x3f803f80,0x3f803f80,0x3f803f80,0x3f803f80,0x3f803f80,0x3f803f80,0x3f803f80,0x3f803f80,0x3f803f80,0x3f803f80,0x3f803f80,
  0x3f803f80,0x3f803f80,0x3f803f80,0x3f803f80,0x3f803f80,0x3f803f80,0x3f803f80,0x3f803f80,0x3f803f80,0x3f803f80,0x3f803f80,0x3f803f80,
  0x3f803f80,0x3f803f80,0x3f803f80,0x3f803f80,0x3f803f80,0x3f803f80,0x3f803f80,0x3f803f80,0x3f803f80,0x3f803f80,0x3f803f80,0x3f803f80,
  0x3f803f80,0x3f803f80,0x3f803f80,0x3f803f80,0x3f803f80,0x3f803f80,0x3f803f80,0x3f803f80,0x3f803f80,0x3f803f80,0x3f803f80,0x3f803f80,
  0x3f803f80,0x3f803f80,0x3f803f80,0x3f803f80,0x3f803f80,0x3f803f80,0x3f803f80,0x3f803f80,0x3f803f80,0x3f803f80,0x3f803f80,0x3f803f80,
  0x3f803f80,0x3f803f80,0x3f803f80,0x3f803f80,0x3f803f80,0x3f803f80,0x3f803f80,0x3f803f80,0x3f803f80,0x3f803f80,0x3f803f80,0x3f803f80,
  0x3f803f80,0x3f803f80,0x3f803f80,0x3f803f80,
};

__device__ __align__(128) float    g_part[16][8][2176];
__device__ __align__(128) float    g_kv[16][2176];
__device__ __align__(128) uint4    g_o[16 * 16 * 1024];
__device__ __align__(128) unsigned g_ocnt[2 * 16 * 32];
__device__ unsigned g_epoch[128];
#define GSTAMP(role, i) do {} while (0)
#define STAMP(role, i) do {} while (0)
#define PDUMP(role) do {} while (0)
#define PROF_SMEM 0

constexpr int STAGE_BYTES = 57344;
constexpr int OFF_H = 4 * 16384, OFF_VP = 9 * 16384, OFF_SPARE = 10 * 16384;
constexpr int OFF_XT = 172032, XT_STRIDE = 4112;
constexpr int OFF_BAR = 204928, OFF_EPOCH = OFF_BAR + 640, OFF_EX = OFF_BAR + 656, OFF_D = OFF_BAR + 672, OFF_SCALE = OFF_BAR + 704;
constexpr int OFF_F2F = 205824, OFF_F2I = 207872, OFF_F4 = 209920, OFF_ONES = 214016, OFF_KVB = 214016;
constexpr int OFF_STG = 219136, STG_STRIDE = 4352, SMEM_TOTAL = 232192 + PROF_SMEM;
enum { B_FULL1 = 0, B_EMPTY1 = 3, B_Q = 6, B_ODONE1 = 7, B_O1RDY = 8, B_H = 9, B_XRAW = 10, B_XT = 11, B_KV = 12, B_Y = 13,  B_AFREE = 15,
       B_STG = 18, B_ODONE = 24, B_XFREE = 25, B_FULL2 = 33, B_CONS2 = 49, B_SFREE = 14, B_PKRDY = 62, B_PKFREE = 64, B_H2 = 65, B_G1DONE = 66, B_COUNT = 67 };
__host__ __device__ constexpr int bar_count(int i) {
  return i < B_EMPTY1 ? 1 : i < B_Q ? 4 : i == B_XT ? 4 : i == B_H ? 4 : (i == B_SFREE || i == B_G1DONE) ? 2 : i >= B_PKFREE ? 4 : i >= B_PKRDY ? 8 : i == B_KV ? 2 : i == B_Y ? 9
       : (i >= B_AFREE && i < B_STG) ? 16 : (i == B_ODONE || i == B_ODONE1) ? 8 : (i >= B_XFREE && i < B_FULL2) ? 4
       : i >= B_CONS2 ? 4 : (i >= B_FULL2 && i < B_FULL2 + 7) ? 2 : 1;
}
__host__ __device__ constexpr uint64_t bar_counts(int r) {
  uint64_t v = 0;
  for (int w = 0; w < 11; w++) v |= (uint64_t)(bar_count(1 + 11 * r + w) - 1) << (4 * w);
  return v;
}
constexpr uint64_t SLOT_A = 0x9645296452964594ull;
constexpr uint64_t SLOT_B = 0x7103871038710326ull;
constexpr uint32_t SW128 = 64 | (1u << 30);
constexpr int SPIN_LIMIT = 1 << 22;
#define PKV CU_TENSOR_MAP_L2_PROMOTION_L2_128B
#define BPRE B_KV
#define PFD 3
#define PD1 600
#define PD2 200
#define E1C 2
#define OSP 4
#define QPF 6
#define TSPLIT 1
#define OC0 2
#define OC1 2
#define BSPL 4
#define BPACE 250
#define NPOS 0
#define O1POS 1
#define HL1 4
#define OCH 3
#define O1D 1
#define QPOS 2
#define HOLD2 12
#define A0COL 0
#define KPOS 1
#define CWAIT 0
#define HSPL 32
#define BEARLY 3
#define BLATE B_KV
#define G2LA 0
#define G2W0 0
#define G2S 2
#define EPI2 1
#define X0U 1
#define S1E 0
#define D1 200
#define PREWPOS 0
#define TRICK 3
#define HSTART 1500
#define PACE 800
#define OC 1

__device__ __forceinline__ uint32_t smem_u32(const void* p) { return (uint32_t)__cvta_generic_to_shared(p); }
__device__ __forceinline__ void wg_fence() { asm volatile("wgmma.fence.sync.aligned;" ::: "memory"); }
__device__ __forceinline__ void wg_commit() { asm volatile("wgmma.commit_group.sync.aligned;" ::: "memory"); }
template <int N> __device__ __forceinline__ void wg_wait() { asm volatile("wgmma.wait_group.sync.aligned %0;" ::"n"(N) : "memory"); }
template <int N> __device__ __forceinline__ void keep(float (&d)[N]) {
#pragma unroll
  for (int i = 0; i < N; i++) asm volatile("" : "+f"(d[i])::"memory");
}
__device__ __forceinline__ uint64_t mkdesc(uint32_t addr, uint32_t lbo, uint32_t sbo, uint32_t swz) {
  uint32_t lo = ((addr & 0x3FFFF) >> 4) | ((lbo >> 4) << 16), hi = (sbo >> 4) | (swz << 30);
  return ((uint64_t)hi << 32) | lo;
}
__device__ __forceinline__ void mbar_init(uint32_t bar, int cnt) { asm volatile("mbarrier.init.shared::cta.b64 [%0], %1;" ::"r"(bar), "r"(cnt)); }
__device__ __forceinline__ void mbar_expect(uint32_t bar, int bytes) { asm volatile("mbarrier.arrive.expect_tx.shared::cta.b64 _, [%0], %1;" ::"r"(bar), "r"(bytes) : "memory"); }
__device__ __forceinline__ void mbar_arrive(uint32_t bar) { asm volatile("mbarrier.arrive.shared::cta.b64 _, [%0];" ::"r"(bar) : "memory"); }
__device__ __forceinline__ void mbar_arrive_cl(uint32_t bar, uint32_t cta) {
  asm volatile("{\n.reg .b32 r;\nmapa.shared::cluster.u32 r, %0, %1;\nmbarrier.arrive.shared::cluster.b64 _, [r];\n}\n" ::"r"(bar), "r"(cta) : "memory");
}
__device__ __forceinline__ void mbar_wait(uint32_t bar, uint32_t parity) {
  asm volatile("{\n.reg .pred p;\n.reg .u32 n;\nmov.u32 n, 0;\n"
               "W_%=:\nmbarrier.try_wait.parity.shared::cta.b64 p, [%0], %1;\n@p bra D_%=;\n"
               "add.u32 n, n, 1;\nsetp.lt.u32 p, n, %2;\n@p bra W_%=;\ntrap;\nD_%=:\n}\n" ::"r"(bar), "r"(parity), "n"(SPIN_LIMIT) : "memory");
}
__device__ __forceinline__ void fence_async() { asm volatile("fence.proxy.async.shared::cta;" ::: "memory"); }
__device__ __forceinline__ void bar_sync(int id) { asm volatile("bar.sync %0, 128;" ::"r"(id) : "memory"); }
__device__ __forceinline__ void tma2d(uint32_t dst, const CUtensorMap* m, int c0, int c1, uint32_t bar) {
  asm volatile("cp.async.bulk.tensor.2d.shared::cluster.global.mbarrier::complete_tx::bytes [%0], [%1, {%3, %4}], [%2];"
               ::"r"(dst), "l"(m), "r"(bar), "r"(c0), "r"(c1) : "memory");
}
__device__ __forceinline__ void tma2d_mc(uint32_t dst, const CUtensorMap* m, int c0, int c1, uint32_t bar) {
  asm volatile("cp.async.bulk.tensor.2d.shared::cluster.global.mbarrier::complete_tx::bytes.multicast::cluster [%0], [%1, {%3, %4}], [%2], %5;"
               ::"r"(dst), "l"(m), "r"(bar), "r"(c0), "r"(c1), "h"((uint16_t)3) : "memory");
}
__device__ __forceinline__ void tma3d(uint32_t dst, const CUtensorMap* m, int c0, int c1, int c2, uint32_t bar) {
  asm volatile("cp.async.bulk.tensor.3d.shared::cluster.global.mbarrier::complete_tx::bytes [%0], [%1, {%3, %4, %5}], [%2];"
               ::"r"(dst), "l"(m), "r"(bar), "r"(c0), "r"(c1), "r"(c2) : "memory");
}
__device__ __forceinline__ void tma4d(uint32_t dst, const CUtensorMap* m, int c0, int c1, int c2, int c3, uint32_t bar) {
  asm volatile("cp.async.bulk.tensor.4d.shared::cluster.global.mbarrier::complete_tx::bytes [%0], [%1, {%3, %4, %5, %6}], [%2];"
               ::"r"(dst), "l"(m), "r"(bar), "r"(c0), "r"(c1), "r"(c2), "r"(c3) : "memory");
}
__device__ __forceinline__ void bulk_ld(uint32_t dst, const void* src, int bytes, uint32_t bar) {
  asm volatile("cp.async.bulk.shared::cluster.global.mbarrier::complete_tx::bytes [%0], [%1], %2, [%3];" ::"r"(dst), "l"(src), "r"(bytes), "r"(bar) : "memory");
}
__device__ __forceinline__ void bulk_ld_mc(uint32_t dst, const void* src, int bytes, uint32_t bar) {
  asm volatile("cp.async.bulk.shared::cluster.global.mbarrier::complete_tx::bytes.multicast::cluster [%0], [%1], %2, [%3], %4;"
               ::"r"(dst), "l"(src), "r"(bytes), "r"(bar), "h"((uint16_t)3) : "memory");
}
__device__ __forceinline__ void tma2d_st(const CUtensorMap* m, uint32_t src, int c0, int c1) {
  asm volatile("cp.async.bulk.tensor.2d.global.shared::cta.bulk_group [%0, {%2, %3}], [%1];" ::"l"(m), "r"(src), "r"(c0), "r"(c1) : "memory");
}
__device__ __forceinline__ void pf_l2(const void* p, int bytes) { asm volatile("cp.async.bulk.prefetch.L2.global [%0], %1;" ::"l"(p), "r"(bytes) : "memory"); }
__device__ __forceinline__ void pf_t2d(const CUtensorMap* m, int c0, int c1) {
  asm volatile("cp.async.bulk.prefetch.tensor.2d.L2.global [%0, {%1, %2}];" ::"l"(m), "r"(c0), "r"(c1) : "memory");
}
__device__ __forceinline__ void pf_t3d(const CUtensorMap* m, int c0, int c1, int c2) {
  asm volatile("cp.async.bulk.prefetch.tensor.3d.L2.global [%0, {%1, %2, %3}];" ::"l"(m), "r"(c0), "r"(c1), "r"(c2) : "memory");
}
__device__ __forceinline__ void ldsm4(uint32_t (&r)[4], uint32_t a) {
  asm volatile("ldmatrix.sync.aligned.m8n8.x4.shared.b16 {%0,%1,%2,%3}, [%4];" : "=r"(r[0]), "=r"(r[1]), "=r"(r[2]), "=r"(r[3]) : "r"(a) : "memory");
}
__device__ __forceinline__ void ldsm4t(uint32_t (&r)[4], uint32_t a) {
  asm volatile("ldmatrix.sync.aligned.m8n8.x4.trans.shared.b16 {%0,%1,%2,%3}, [%4];" : "=r"(r[0]), "=r"(r[1]), "=r"(r[2]), "=r"(r[3]) : "r"(a) : "memory");
}
__device__ __forceinline__ void stsm4(uint32_t a, uint32_t r0, uint32_t r1, uint32_t r2, uint32_t r3) {
  asm volatile("stmatrix.sync.aligned.m8n8.x4.shared.b16 [%0], {%1,%2,%3,%4};" ::"r"(a), "r"(r0), "r"(r1), "r"(r2), "r"(r3) : "memory");
}
__device__ __forceinline__ uint32_t pk2(float lo, float hi) { uint32_t r; asm("cvt.rn.bf16x2.f32 %0, %1, %2;" : "=r"(r) : "f"(hi), "f"(lo)); return r; }
__device__ __forceinline__ uint32_t hmul(uint32_t a, uint32_t b) { uint32_t r; asm("mul.rn.bf16x2 %0, %1, %2;" : "=r"(r) : "r"(a), "r"(b)); return r; }
__device__ __forceinline__ uint32_t hadd(uint32_t a, uint32_t b) { uint32_t r; asm("add.rn.bf16x2 %0, %1, %2;" : "=r"(r) : "r"(a), "r"(b)); return r; }
__device__ __forceinline__ uint32_t hmax(uint32_t a, uint32_t b) { uint32_t r; asm("max.bf16x2 %0, %1, %2;" : "=r"(r) : "r"(a), "r"(b)); return r; }
__device__ __forceinline__ uint32_t hmin(uint32_t a, uint32_t b) { uint32_t r; asm("min.bf16x2 %0, %1, %2;" : "=r"(r) : "r"(a), "r"(b)); return r; }
__device__ __forceinline__ uint32_t hmaxabs(uint32_t a, uint32_t b) { uint32_t r; asm("max.xorsign.abs.bf16x2 %0, %1, %2;" : "=r"(r) : "r"(a), "r"(b)); return r; }
__device__ __forceinline__ float ex2(float x) { float r; asm("ex2.approx.ftz.f32 %0, %1;" : "=f"(r) : "f"(x)); return r; }
__device__ __forceinline__ float rcp_fast(float x) { float r; asm("rcp.approx.ftz.f32 %0, %1;" : "=f"(r) : "f"(x)); return r; }
__device__ __forceinline__ uint32_t phi2(float lo, float hi) {
  uint32_t t;
  asm("cvt.rn.relu.bf16x2.f32 %0, %1, %2;" : "=r"(t) : "f"(hi), "f"(lo));
  const uint32_t e = pk2(ex2(lo * 1.4426950408889634f), ex2(hi * 1.4426950408889634f));
  return hadd(hadd(t, hmin(e, 0x3F803F80u)), 0x35863586u);
}
__device__ __forceinline__ bool opaque_true() { uint32_t v; asm volatile("mov.u32 %0, %%nctaid.y;" : "=r"(v)); return v != 0; }
__device__ __forceinline__ int norm_exp(uint32_t (&v)[32], float f0) {
  uint32_t m[4] = {hmaxabs(__float_as_uint(f0) >> 16, v[0]), v[1], v[2], v[3]};
#pragma unroll
  for (int i = 4; i < 32; i++) m[i & 3] = hmaxabs(m[i & 3], v[i]);
  m[0] = hmaxabs(hmaxabs(m[0], m[1]), hmaxabs(m[2], m[3]));
  const int e = min(max((int)(__reduce_max_sync(~0u, max(m[0] & 0x7FFFu, (m[0] >> 16) & 0x7FFFu)) >> 7), 1), 253);
  if (e > 141) {
#pragma unroll
    for (int i = 0; i < 32; i++) v[i] = hmul(v[i], 0x07000700u);
  }
  return e;
}
template <int I0, int I1>
__device__ __forceinline__ void norm_cvt(uint32_t (&v)[32], float f0, int e) {
  const uint32_t sc = (e > 141 ? 255 - e : 142 - e) * 0x00800080u;
#pragma unroll
  for (int i = I0; i < I1; i++) {
    const uint32_t a = hmul(v[i], sc);
    v[i] = (a & 0x0FFF0FFFu) * 7 + a;
  }
  if (I0 == 0) v[0] = __byte_perm(v[0], __half_as_ushort(__float2half_rn(f0 * __uint_as_float((254 - e) << 23))), 0x3254);
}
__device__ __forceinline__ void poll_ge(const unsigned* p, unsigned target) {
#pragma unroll 1
  for (int n = 0; n < SPIN_LIMIT; n++) {
    unsigned v;
    asm volatile("ld.relaxed.gpu.global.u32 %0, [%1];" : "=r"(v) : "l"(p) : "memory");
    if (__all_sync(~0u, (int)(v - target) >= 0)) { asm volatile("fence.acquire.gpu;" ::: "memory"); return; }
  }
  __trap();
}

__device__ __forceinline__ bool elect_one() {
  uint32_t p;
  asm volatile("{\n.reg .pred p;\nelect.sync _|p, 0xffffffff;\nselp.u32 %0, 1, 0, p;\n}\n" : "=r"(p));
  return p;
}
__device__ __forceinline__ uint4 ld_nc4(const void* p) {
  uint4 v;
  asm volatile("ld.global.L1::no_allocate.v4.u32 {%0,%1,%2,%3}, [%4];" : "=r"(v.x), "=r"(v.y), "=r"(v.z), "=r"(v.w) : "l"(p) : "memory");
  return v;
}
__device__ __forceinline__ void st_cg4(void* p, uint4 v) {
  asm volatile("st.global.cg.v4.u32 [%0], {%1,%2,%3,%4};" ::"l"(p), "r"(v.x), "r"(v.y), "r"(v.z), "r"(v.w) : "memory");
}
__device__ __forceinline__ uint32_t mapa(uint32_t a, uint32_t cta) { uint32_t r; asm("mapa.shared::cluster.u32 %0, %1, %2;" : "=r"(r) : "r"(a), "r"(cta)); return r; }
__device__ __forceinline__ void st_async(uint32_t a, uint32_t v, uint32_t bar) {
  asm volatile("st.async.weak.shared::cluster.mbarrier::complete_tx::bytes.b32 [%0], %1, [%2];" ::"r"(a), "r"(v), "r"(bar) : "memory");
}
__device__ __forceinline__ void st_async4(uint32_t a, uint32_t x, uint32_t y, uint32_t z, uint32_t w, uint32_t bar) {
  asm volatile("st.async.weak.shared::cluster.mbarrier::complete_tx::bytes.v4.b32 [%0], {%1,%2,%3,%4}, [%5];" ::"r"(a), "r"(x), "r"(y), "r"(z), "r"(w), "r"(bar) : "memory");
}
__device__ __forceinline__ void tma3d_st(const CUtensorMap* m, uint32_t src, int c0, int c1, int c2) {
  asm volatile("cp.async.bulk.tensor.3d.global.shared::cta.bulk_group [%0, {%2, %3, %4}], [%1];" ::"l"(m), "r"(src), "r"(c0), "r"(c1), "r"(c2) : "memory");
}
__device__ __forceinline__ uint4 ld_rlx4(const void* p) {
  uint4 v;
  asm volatile("{\n.reg .b128 t;\n.reg .b64 a, b;\nld.relaxed.gpu.global.b128 t, [%4];\nmov.b128 {a, b}, t;\nmov.b64 {%0, %1}, a;\nmov.b64 {%2, %3}, b;\n}\n"
               : "=r"(v.x), "=r"(v.y), "=r"(v.z), "=r"(v.w) : "l"(p) : "memory");
  return v;
}
__device__ __forceinline__ void ld_stale4(uint4& v, const void* p, uint32_t tag) {
  asm volatile("{\n.reg .b128 t;\n.reg .b64 a, b;\n.reg .b32 x;\n.reg .pred p;\n"
               "lop3.b32 x, %0, %5, 1, 0x28;\nsetp.ne.u32 p, x, 0;\n"
               "mov.b64 a, {%0, %1};\nmov.b64 b, {%2, %3};\nmov.b128 t, {a, b};\n"
               "@p ld.relaxed.gpu.global.b128 t, [%4];\n"
               "mov.b128 {a, b}, t;\nmov.b64 {%0, %1}, a;\nmov.b64 {%2, %3}, b;\n}\n"
               : "+r"(v.x), "+r"(v.y), "+r"(v.z), "+r"(v.w) : "l"(p), "r"(tag) : "memory");
}
__device__ __forceinline__ void st_tag4(void* p, float a, float b, float c, float d, uint32_t tag) {
  asm volatile("{\n.reg .b128 t;\n.reg .b64 a, b;\nmov.b64 a, {%1, %2};\nmov.b64 b, {%3, %4};\nmov.b128 t, {a, b};\nst.relaxed.gpu.global.b128 [%0], t;\n}\n"
               ::"l"(p), "r"((__float_as_uint(a) & ~1u) | tag), "f"(b), "f"(c), "f"(d) : "memory");
}
__device__ __forceinline__ uint32_t stale8(const uint4 (&f)[8], uint32_t tag) {
  uint32_t r[4];
#pragma unroll
  for (int i = 0; i < 4; i++) asm("lop3.b32 %0, %1, %2, %3, 0x7E;" : "=r"(r[i]) : "r"(f[2 * i].x), "r"(f[2 * i + 1].x), "r"(tag));
  asm("lop3.b32 %0, %0, %1, %2, 0xFE;" : "+r"(r[0]) : "r"(r[1]), "r"(r[2]));
  return r[0] | r[3];
}

struct ConvC { uint32_t a1[2][4], wa[2], wb[2], sg; };
__device__ __forceinline__ uint64_t dsc(uint32_t lo, uint32_t hi) { return ((uint64_t)hi << 32) | lo; }
__device__ __forceinline__ uint32_t hfma(uint32_t a, uint32_t b, uint32_t c) { uint32_t r; asm("fma.rn.f16x2 %0, %1, %2, %3;" : "=r"(r) : "r"(a), "r"(b), "r"(c)); return r; }
__device__ __forceinline__ uint32_t hfnma(uint32_t a, uint32_t b, uint32_t c) { uint32_t r; asm("{.reg .b32 n; neg.f16x2 n, %1; fma.rn.f16x2 %0, n, %2, %3;}" : "=r"(r) : "r"(a), "r"(b), "r"(c)); return r; }
__device__ __forceinline__ uint32_t hmul16(uint32_t a, uint32_t b) { uint32_t r; asm("mul.rn.f16x2 %0, %1, %2;" : "=r"(r) : "r"(a), "r"(b)); return r; }
template <int N> __device__ __forceinline__ void keepu(uint32_t (&d)[N]) {
#pragma unroll
  for (int i = 0; i < N; i++) asm volatile("" : "+r"(d[i])::"memory");
}
__device__ __forceinline__ void conv_m1(const ConvC& K, uint32_t (&u)[16], uint32_t l) {
  wg_fence();
  wgmma_hrs_n64<1>(u, K.a1[0][0], K.a1[0][1], K.a1[0][2], K.a1[0][3], dsc(l, 32), 0);
  wgmma_hrs_n64<1>(u, K.a1[1][0], K.a1[1][1], K.a1[1][2], K.a1[1][3], dsc(l + 16, 32), 1);
  wg_commit();
}
__device__ __forceinline__ void conv_s2(const ConvC& K, uint32_t (&u)[16], uint32_t (&Z)[2][8], uint32_t dfl) {
  uint32_t fr[8], fi[8];
#pragma unroll
  for (int c = 0; c < 8; c++) {
    const uint32_t r = hfma(K.wa[c & 1], u[2 * c + 1], u[2 * c]);
    fi[c] = hfma(K.wb[c & 1], r, u[2 * c + 1]);
    fr[c] = hfma(K.wa[c & 1], fi[c], r);
  }
  wg_fence();
#pragma unroll
  for (int p = 0; p < 2; p++) {
    wgmma_hrs_n32<0>(Z[p], fr[4 * p], fr[4 * p + 2], fr[4 * p + 1], fr[4 * p + 3], dsc(dfl, 32), 0);
    wgmma_hrs_n32<0>(Z[p], fi[4 * p], fi[4 * p + 2], fi[4 * p + 1], fi[4 * p + 3], dsc(dfl + 16, 32), 1);
  }
  wg_commit();
}
__device__ __forceinline__ void conv_win(const ConvC& K, const uint32_t (&X)[2][8], uint32_t (&W)[2][8]) {
#pragma unroll
  for (int b = 0; b < 4; b++)
#pragma unroll
    for (int c = 0; c < 2; c++) {
      const uint32_t xr = X[b >> 1][2 * c + (b & 1)], xi = X[b >> 1][4 + 2 * c + (b & 1)];
      const int a = b ? b - 1 : 0;
      W[b >> 1][2 * c + (b & 1)] = b ? hfnma(K.sg, X[a >> 1][4 + 2 * c + (a & 1)], xr) : hmul16(xr, 0x3C003C00u);
      W[b >> 1][4 + 2 * c + (b & 1)] = b ? hfma(K.sg, X[a >> 1][2 * c + (a & 1)], xi) : hmul16(xi, 0x3C003C00u);
    }
}
template <int p>
__device__ __forceinline__ void conv_pw(uint32_t (&X)[2][8], uint32_t (&H)[2][8], uint32_t (&V)[8], uint32_t dil) {
  uint32_t pr[2][2], pi[2][2];
#pragma unroll
  for (int jj = 0; jj < 2; jj++)
#pragma unroll
    for (int c = 0; c < 2; c++) {
      const int j = 2 * p + jj;
      uint32_t sr = 0, si = 0;
#pragma unroll
      for (int a = 0; a <= j; a++) {
        const int b = j - a;
        const uint32_t hr = H[a >> 1][2 * c + (a & 1)], hi = H[a >> 1][4 + 2 * c + (a & 1)];
        const uint32_t xr = X[b >> 1][2 * c + (b & 1)], xi = X[b >> 1][4 + 2 * c + (b & 1)];
        sr = a == 0 ? hmul16(hr, xr) : hfma(hr, xr, sr);
        si = a == 0 ? hmul16(hr, xi) : hfma(hr, xi, si);
        sr = hfnma(hi, xi, sr);
        si = hfma(hi, xr, si);
      }
      pr[jj][c] = sr; pi[jj][c] = si;
    }
  wg_fence();
  wgmma_hrs_n32<0>(V, pr[0][0], pr[1][0], pr[0][1], pr[1][1], dsc(dil, 32), 0);
  wgmma_hrs_n32<0>(V, pi[0][0], pi[1][0], pi[0][1], pi[1][1], dsc(dil + 16, 32), 1);
  wg_commit();
}
template <int p>
__device__ __forceinline__ void conv_it(const ConvC& K, uint32_t (&V)[8], uint32_t vst) {
#pragma unroll
  for (int jj = 0; jj < 2; jj++) {
    uint32_t wr[2], wi[2];
#pragma unroll
    for (int c = 0; c < 2; c++) {
      const uint32_t r = hfnma(K.wa[c], V[4 + 2 * c + jj], V[2 * c + jj]);
      wi[c] = hfnma(K.wb[c], r, V[4 + 2 * c + jj]);
      wr[c] = hfnma(K.wa[c], wi[c], r);
    }
    stsm4(vst + (2 * p + jj) * 2048, wr[0], wr[1], wi[0], wi[1]);
  }
}
__device__ __forceinline__ void conv_m4(uint32_t (&y)[8], uint32_t (&a)[4][4], uint32_t d4l) {
  wg_fence();
  wgmma_hrs_n32<0>(y, a[0][0], a[0][1], a[0][2], a[0][3], dsc(d4l, 64), 0);
#pragma unroll
  for (int s = 1; s < 4; s++) wgmma_hrs_n32<0>(y, a[s][0], a[s][1], a[s][2], a[s][3], dsc(d4l + s * 16, 64), 1);
  wg_commit();
}

struct Params {
  CUtensorMap tmX, tmW, tmWo, tmWo1, tmK, tmV, tmQ, tmOA, tmOB;
  const __nv_bfloat16 *shift_k, *h, *D, *x, *w, *wo, *q;
  float *part, *kv;
  uint4* o;
  unsigned *ocnt, *epoch;
  const uint32_t *thr, *img;
};

__global__ void __cluster_dims__(2, 1, 1) __launch_bounds__(384, 1) fused_kernel(const __grid_constant__ Params P) {
  extern __shared__ __align__(1024) uint8_t smem[];
  const uint32_t sb = __shfl_sync(~0u, smem_u32(smem), 0);
  const uint32_t bars = sb + OFF_BAR;
  const int tid = threadIdx.x, lane = tid & 31;
  const int warp = __shfl_sync(~0u, tid >> 5, 0);
  const int rank = blockIdx.x & 1, cl = blockIdx.x >> 1;
  const int mb = cl < 4 ? 4 + cl : cl < 36 ? (cl - 4) >> 3 : 4 + (cl - 36) / 7;
  const int hb = (cl - 36) % 7;
  const int hq = cl < 4 ? A0COL : cl < 36 ? (cl - 4) & 7 : hb + (hb >= A0COL);
  const int hp = 2 * hq + rank;
  const int rb = 2 * mb + (hq >> 2), cb = hq & 3;
#define BAR(i) (bars + 8 * (i))

  if (tid == 0) { STAMP(0, 0); GSTAMP(0, 30); }
  if (warp == 8) {
    if (elect_one()) {
      mbar_init(BAR(B_FULL1), 1);
      asm volatile("fence.mbarrier_init.release.cluster;" ::: "memory");
      mbar_expect(BAR(B_FULL1), STAGE_BYTES);
      if (X0U == 1) { tma2d(sb, &P.tmX, 0, mb * 256, BAR(B_FULL1)); tma2d(sb + 16384, &P.tmX, 0, mb * 256 + 128, BAR(B_FULL1)); }
      tma3d(sb + 32768, &P.tmW, hp * 64, 0, 0, BAR(B_FULL1));
      if (X0U == 2) { tma2d(sb, &P.tmX, 0, mb * 256, BAR(B_FULL1)); tma2d(sb + 16384, &P.tmX, 0, mb * 256 + 128, BAR(B_FULL1)); }
    }
    if (lane == 0) STAMP(3, 21);
  } else if (lane == 0) {
    const int wi = warp - (warp > 8);
#pragma unroll
    for (int r = 0; r < 6; r++)
      if (r < 5 || wi < B_COUNT - 56) mbar_init(BAR(1 + 11 * r + wi), ((uint32_t)(bar_counts(r) >> (4 * wi)) & 15) + 1);
    asm volatile("fence.mbarrier_init.release.cluster;" ::: "memory");
  }
  if (tid == 0) STAMP(2, 6);
  asm volatile("barrier.cluster.arrive.relaxed.aligned;\nbarrier.cluster.wait.aligned;" ::: "memory");
  if (warp == 8 && elect_one()) {
    if (!X0U) tma2d_mc(sb + rank * 16384, &P.tmX, 0, mb * 256 + rank * 128, BAR(B_FULL1));
    if (S1E) {
      mbar_expect(BAR(B_FULL1 + 1), STAGE_BYTES);
      tma2d_mc(sb + STAGE_BYTES + rank * 16384, &P.tmX, 64, mb * 256 + rank * 128, BAR(B_FULL1 + 1));
      tma3d(sb + STAGE_BYTES + 32768, &P.tmW, hp * 64, 64, 0, BAR(B_FULL1 + 1));
    }
  }
  if (tid == 256) STAMP(2, 7);

  if (warp < 8) {
    asm volatile("setmaxnreg.inc.sync.aligned.u32 224;");
    const int wg = warp >> 2, w = warp & 3, g = lane >> 2, q = lane & 3, t = tid & 127;
    const bool elect = (t == 0);
    const uint32_t s16 = (sb & 0x3FFFF) >> 4;
    uint32_t pq[2][16];
    ConvC K;
    {
      float acc[2][96];
      int st = 0, ph = 0;
#pragma unroll 1
      for (int kb = 0; kb < 14; kb++) {
        mbar_wait(BAR(B_FULL1 + st), ph);
        if (kb == 0 && elect) { STAMP(wg, 1); GSTAMP(wg, 26); }
        if (kb == 8 && elect) { STAMP(wg, 16); GSTAMP(wg, 25); }
        if (G2S == 3 && tid == 0) STAMP(2, 8 + kb);
        const uint32_t da = s16 + st * (STAGE_BYTES >> 4) + wg * 1024 + (1 << 16);
        const uint32_t db = s16 + st * (STAGE_BYTES >> 4) + 2048 + (512 << 16);
        wg_fence();
#pragma unroll
        for (int ks = 0; ks < 4; ks++) {
          wgmma_ss_n192<0, 1>(acc[0], dsc(da + ks * 2, SW128), dsc(db + ks * 128, SW128), (kb | ks) != 0);
          wgmma_ss_n192<0, 1>(acc[1], dsc(da + 512 + ks * 2, SW128), dsc(db + ks * 128, SW128), (kb | ks) != 0);
        }
        wg_commit();
        wg_wait<1>();
        if (kb > 0 && t < 2) mbar_arrive_cl(BAR(B_EMPTY1 + (st == 0 ? 2 : st - 1)), t);
        if (++st == 3) { st = 0; ph ^= 1; }
      }
#define TAIL_MMA(mt, stage) do { wg_fence(); _Pragma("unroll") for (int ks = 0; ks < 4; ks++) \
        wgmma_ss_n192<0, 1>(acc[mt], dsc(s16 + (stage) * (STAGE_BYTES >> 4) + wg * 1024 + (mt) * 512 + (1 << 16) + ks * 2, SW128), \
                            dsc(s16 + (stage) * (STAGE_BYTES >> 4) + 2048 + (512 << 16) + ks * 128, SW128), 1); wg_commit(); } while (0)
      mbar_wait(BAR(B_FULL1 + 2), 0);
      TAIL_MMA(0, 2);
      wg_wait<1>();
      if (elect) mbar_arrive(BAR(B_SFREE));
      mbar_wait(BAR(B_FULL1 + 0), 1);
      TAIL_MMA(0, 0);
      TAIL_MMA(1, 2);
      const uint32_t lrow = sb + wg * 16384 + (16 * w + 8 * ((lane >> 3) & 1) + (lane & 7)) * 128 + (((lane >> 4) ^ (lane & 7)) << 4);
#define E1K(mt, i) do { if (opaque_true()) { _Pragma("unroll") for (int j = (i); j < (i) + 2; j++) { \
          const float* a = &acc[mt][32 + 8 * j]; const float* b = a + 32; const uint32_t o = (lrow ^ (j * 32)) + (mt) * 8192; \
          stsm4(o + 2 * STAGE_BYTES, pk2(b[0], b[1]), pk2(b[2], b[3]), pk2(b[4], b[5]), pk2(b[6], b[7])); \
          stsm4(o, phi2(a[0], a[1]), phi2(a[2], a[3]), phi2(a[4], a[5]), phi2(a[6], a[7])); } } } while (0)
#define E1Q(mt) do { if (opaque_true()) { _Pragma("unroll") for (int i = 0; i < 16; i++) pq[mt][i] = phi2(acc[mt][2 * i], acc[mt][2 * i + 1]); } } while (0)
#define PK_READY(mt) do { fence_async(); __syncwarp(); if (lane == 0) mbar_arrive(BAR(B_PKRDY + (mt))); } while (0)
      wg_wait<1>();
      keep(acc[0]);
      if (elect) STAMP(wg, 18);
      E1K(0, 0);
      TAIL_MMA(1, 0);
      E1K(0, 2);
      if (elect) STAMP(wg, 19);
      PK_READY(0);
      wg_wait<0>();
      keep(acc[1]);
      if (elect) mbar_arrive(BAR(B_G1DONE));
      asm volatile("setmaxnreg.dec.sync.aligned.u32 200;");
      if (elect) { STAMP(wg, 2); GSTAMP(wg, 27); }
      E1K(1, 0);
      E1K(1, 2);
      PK_READY(1);
      if (elect) STAMP(wg, 3);
      {
        const uint4* ct = (const uint4*)P.thr + t;
#pragma unroll
        for (int s = 0; s < 2; s++) { const uint4 u = ld_nc4(ct + s * 128); K.a1[s][0] = u.x; K.a1[s][1] = u.y; K.a1[s][2] = u.z; K.a1[s][3] = u.w; }
        const uint4 u = ld_nc4(ct + 2 * 128);
        K.wa[0] = u.x; K.wa[1] = u.y; K.wb[0] = u.z; K.wb[1] = u.w;
        K.sg = (lane & 4) ? 0xBC00BC00u : 0x3C003C00u;
      }
      if (CWAIT) mbar_wait(BAR(B_PKFREE), 0);
      if (elect) STAMP(wg, 4);
      E1Q(0);
      E1Q(1);
    }
    if (elect) STAMP(wg, 17);
    mbar_wait(BAR(B_H), 0);
    mbar_wait(BAR(B_PKRDY + 1), 0);
    if (elect) STAMP(wg, 5);
    {
      const uint32_t dfl = s16 + (OFF_F2F >> 4) + (8 << 16), dil = s16 + (OFF_F2I >> 4) + (8 << 16), d4l = s16 + (OFF_F4 >> 4) + (8 << 16);
      const uint32_t xl = s16 + (OFF_XT >> 4) + 4 * wg * (XT_STRIDE >> 4) + (8 << 16);
      const uint32_t hl = s16 + (OFF_H >> 4) + wg * 512 + (8 << 16);
      uint32_t vst = sb + wg * 8192 + w * 512 + lane * 16, vld = sb + wg * 8192 + w * 2048 + lane * 16;
      uint32_t ya = mapa(sb + OFF_XT + 4 * wg * XT_STRIDE + (2 * rank + (w & 1)) * 1024 + lane * 16, w >> 1);
      const uint32_t ybar = mapa(BAR(B_Y), w >> 1);
      asm volatile("" : "+r"(vst), "+r"(vld), "+r"(ya));
      uint32_t ux[16], uh[16], W[2][8], V0[8], V1[8], y[8], a[4][4];
      uint4 ov[4];
      uint4* const ot = P.o + ((2 * mb + wg) * 16 + hq) * 1024 + (16 * w + g) * 8 + ((4 * rank + q) ^ g);
#define YOUT(i) do { if ((w >> 1) == rank) { \
          asm volatile("st.shared.v4.b32 [%0], {%1,%2,%3,%4};" ::"r"(ya + (i) * XT_STRIDE), "r"(y[0]), "r"(y[2]), "r"(y[4]), "r"(y[6]) : "memory"); \
          asm volatile("st.shared.v4.b32 [%0], {%1,%2,%3,%4};" ::"r"(ya + (i) * XT_STRIDE + 512), "r"(y[1]), "r"(y[3]), "r"(y[5]), "r"(y[7]) : "memory"); \
        } else { \
          mbar_wait(BAR(B_XFREE + 4 * wg + (i)), 0); \
          st_async4(ya + (i) * XT_STRIDE, y[0], y[2], y[4], y[6], ybar); \
          st_async4(ya + (i) * XT_STRIDE + 512, y[1], y[3], y[5], y[7], ybar); } } while (0)
      auto ocalc = [&](const int hh) {
        if (hh == 0) {
          if (elect) STAMP(wg, 8);
          mbar_wait(BAR(B_KV), 0);
          if (elect) STAMP(wg, 9);
        }
        float oa[2][20];
        wg_fence();
#pragma unroll
        for (int m = 0; m < 4; m++) {
          const uint32_t* p = &pq[m & 1][8 * hh + 4 * (m >> 1)];
          wgmma_rs_n40<1>(oa[m & 1], p[0], p[1], p[2], p[3], dsc(s16 + (OFF_KVB >> 4) + hh * 160 + (m >> 1) * 16 + (8 << 16), 32), m >> 1);
        }
        wg_commit();
        wg_wait<0>();
#pragma unroll
        for (int mt = 0; mt < 2; mt++) {
          float (&o)[20] = oa[mt];
          keep(o);
          const uint32_t den = hadd(pk2(o[16], o[18]), 0x35863586u);
#pragma unroll
          for (int r = 0; r < 2; r++) {
            const float ri = rcp_fast(__uint_as_float(r ? (den & 0xFFFF0000u) : (den << 16)));
            uint4 u;
            u.x = pk2(o[2 * r] * ri, o[2 * r + 1] * ri);
            u.y = pk2(o[4 + 2 * r] * ri, o[5 + 2 * r] * ri);
            u.z = pk2(o[8 + 2 * r] * ri, o[9 + 2 * r] * ri);
            u.w = pk2(o[12 + 2 * r] * ri, o[13 + 2 * r] * ri);
            if (hh == 0 || !TRICK) st_cg4(ot + hh * 8 * 1024 + (64 * mt + 8 * r) * 8, u); else ov[2 * mt + r] = u;
          }
        }
        if (hh == 1 && TRICK) return;
        __syncwarp();
        if (lane == 0) mbar_arrive(BAR(hh ? B_ODONE1 : B_ODONE));
        if (hh == 0 && elect) STAMP(wg, 10);
      };
      auto trickle = [&](const int qs) {
        const int m = qs - 2 * (OCH + O1D) - (TRICK - 1);
        if (TRICK && m >= 0 && m < 4) {
          st_cg4(ot + 8 * 1024 + (64 * (m >> 1) + 8 * (m & 1)) * 8, ov[m]);
          if (m == 3) { __syncwarp(); if (lane == 0) mbar_arrive(BAR(B_ODONE1)); }
        }
      };
      uint32_t X[4][2][8], H[4][2][8];
      conv_m1(K, ux, xl);
      conv_m1(K, uh, hl);
      wg_wait<1>(); keepu(ux);
      if (lane == 0) mbar_arrive_cl(BAR(B_XFREE + 4 * wg), rank ^ 1);
      conv_s2(K, ux, X[0], dfl);
      wg_wait<1>(); keepu(uh);
      conv_s2(K, uh, H[0], dfl);
#pragma unroll
      for (int i = 0; i < 4; i++) {
        const bool nx = i < 3;
        const int n = nx ? i + 1 : i;
        const uint32_t vo = (i & 1) ? OFF_H + (i >> 1) * 16384 : OFF_VP;
        if (2 * i == OCH) ocalc(0);
        if (2 * i == OCH + O1D) ocalc(1);
        if (nx) {
          if (n == 2) mbar_wait(BAR(B_H2), 0);
          conv_m1(K, ux, xl + n * (XT_STRIDE >> 4));
          conv_m1(K, uh, hl + (n >> 1) * 1024 + (n & 1) * 256);
        }
        if (2 * i != OCH && 2 * i != OCH + O1D) { if (nx) { if (i > 0) wg_wait<3>(); else wg_wait<2>(); } else wg_wait<1>(); }
        keepu(X[i][0]); keepu(X[i][1]); keepu(H[i][0]); keepu(H[i][1]);
        conv_win(K, X[i], W);
        trickle(4 * i);
        conv_pw<0>(W, H[i], V0, dil);
        conv_pw<1>(W, H[i], V1, dil);
        trickle(4 * i + 1);
        wg_wait<2>();
        if (i > 0) { keepu(y); YOUT(i - 1); }
        if (2 * i + 1 == OCH) ocalc(0);
        if (2 * i + 1 == OCH + O1D) ocalc(1);
        if (nx) {
          keepu(ux); keepu(uh);
          if (lane == 0) mbar_arrive_cl(BAR(B_XFREE + 4 * wg + n), rank ^ 1);
          conv_s2(K, ux, X[n], dfl);
          wg_wait<1>();
        } else wg_wait<0>();
        keepu(V0); keepu(V1);
        trickle(4 * i + 2);
        conv_it<0>(K, V0, vst + vo);
        conv_it<1>(K, V1, vst + vo);
        bar_sync(1 + wg);
#pragma unroll
        for (int s = 0; s < 4; s++) ldsm4t(a[s], vld + vo + s * 512);
        if (nx) conv_s2(K, uh, H[n], dfl);
        conv_m4(y, a, d4l);
        trickle(4 * i + 3);
        if (i > 0 && lane < 2) mbar_arrive_cl(BAR(B_AFREE + i - 1), lane);
        if (elect && i < 3) STAMP(wg, i < 2 ? 6 + i : 9 + i);
      }
      wg_wait<0>(); keepu(y);
      YOUT(3);
      if (OCH + O1D >= 8) ocalc(1);
      __syncwarp();
      if (lane == 0) mbar_arrive(BAR(B_Y));
      if (elect) STAMP(wg, 12);
    }
    {
      float acc[64];
#define G2_MMA(da, db, first) do { wg_fence(); _Pragma("unroll") for (int ks = 0; ks < 4; ks++) \
        wgmma_ss_n128<0, 1>(acc, dsc((da) + ks * 2, SW128), dsc((db) + ks * 128, SW128), ks || !(first)); wg_commit(); } while (0)
      const uint32_t a0 = s16 + wg * 512 + (1 << 16), b0 = s16 + (512 << 16);
      uint64_t ta = SLOT_A, tb = SLOT_B;
      uint32_t da = a0 + (SLOT_A & 15) * 1024, db = b0 + (SLOT_B & 15) * 1024, fb = BAR(B_FULL2);
      uint32_t cons = mapa(BAR(B_CONS2 - 1), t & 1);
      const bool rel = __shfl_sync(~0u, t, lane) < 2;
#pragma unroll 1
      for (int kb = 0; kb < HOLD2; kb++) {
        if (G2S == 0 && tid == 128) STAMP(2, 8 + kb);
        mbar_wait(fb, 0);
        if (G2S == 1 && tid == 128) STAMP(2, 8 + kb);
        if (kb == 0 && elect) { STAMP(wg, 13); GSTAMP(wg, 28); }
        G2_MMA(da, db, kb == 0);
        ta >>= 4; tb >>= 4;
        da = a0 + ((uint32_t)ta & 15) * 1024; db = b0 + ((uint32_t)tb & 15) * 1024; fb += 8;
        asm volatile("" : "+r"(da), "+r"(db));
        wg_wait<1>();
        if (kb > 0 && kb < 12 && rel) asm volatile("mbarrier.arrive.shared::cluster.b64 _, [%0];" ::"r"(cons) : "memory");
        cons += 8;
      }
      if (HOLD2 == 11) { wg_wait<0>(); if (rel) asm volatile("mbarrier.arrive.shared::cluster.b64 _, [%0];" ::"r"(cons) : "memory"); }
#pragma unroll
      for (int kb = HOLD2; kb < 16; kb++) {
        if (wg == 1) mbar_wait(BAR(B_FULL2 + kb), 0);
        else if (kb == HOLD2) asm volatile("bar.sync 3, 256;" ::: "memory");
        G2_MMA(a0 + ((SLOT_A >> (4 * kb)) & 15) * 1024, b0 + ((SLOT_B >> (4 * kb)) & 15) * 1024, false);
      }
      if (wg == 1) asm volatile("bar.arrive 3, 256;" ::: "memory");
      const uint32_t stg = sb + wg * 8192 + w * 2048, so0 = ((SLOT_A >> 56) & 15) * 16384, so1 = ((SLOT_A >> 60) & 15) * 16384;
      const uint32_t lrow = stg + (8 * ((lane >> 3) & 1) + (lane & 7)) * 128 + (((lane >> 4) ^ (lane & 7)) << 4);
      const int col = 1024 + 256 * cb + 128 * rank, row = 128 * rb + 64 * wg + 16 * w;
      wg_wait<0>();
      keep(acc);
      if (elect) { STAMP(wg, 14); GSTAMP(wg, 29); }
#pragma unroll
      for (int cp = 0; cp < 8; cp++) {
        const float* a = &acc[8 * cp];
        stsm4((lrow ^ ((cp & 3) * 32)) + (cp >> 2 ? so1 : so0), pk2(a[0], a[1]), pk2(a[2], a[3]), pk2(a[4], a[5]), pk2(a[6], a[7]));
        if (cp == 7 || (EPI2 && cp == 3)) {
          fence_async();
          __syncwarp();
          if (elect_one()) {
            if (cp == 3 || !EPI2) tma2d_st(&P.tmOB, stg + so0, col, row);
            if (cp == 7) tma2d_st(&P.tmOB, stg + so1, col + 64, row);
          }
        }
      }
      asm volatile("cp.async.bulk.commit_group;\ncp.async.bulk.wait_group.read 0;" ::: "memory");
      if (elect) {
        STAMP(wg, 15); GSTAMP(wg, 31); PDUMP(wg); if (wg == 0) PDUMP(2);
      }
    }
  } else {
    asm volatile("setmaxnreg.dec.sync.aligned.u32 56;");
    const int hw = warp - 9, g = lane >> 2, q = lane & 3;
#define sbar (bars + 8 * (B_STG - 18) + 16 * warp)
    if (warp == 8) {
      if (D1) __nanosleep(D1);
      int st = 1 + S1E, pp = 1;
      const uint8_t* pfx = (const uint8_t*)P.x + (mb * 256 + hp * 16 + (lane & 15)) * 2048;
      const uint8_t* pfw = (const uint8_t*)P.w + (mb * 8 + (lane & 7)) * 6144 + (lane >> 3) * 2048 + hp * 128;
#pragma unroll 1
      for (int kb = 1 + S1E; kb < 16; kb++) {
        if (kb >= 3) mbar_wait(BAR(B_EMPTY1 + st), pp);
        const uint32_t sa = sb + st * STAGE_BYTES;
        if (elect_one()) {
          mbar_expect(BAR(B_FULL1 + st), STAGE_BYTES);
          tma2d_mc(sa + rank * 16384, &P.tmX, kb * 64, mb * 256 + rank * 128, BAR(B_FULL1 + st));
          tma3d(sa + 32768, &P.tmW, hp * 64, kb * 64, 0, BAR(B_FULL1 + st));
        }
        if (kb == 1 && lane == 0) STAMP(2, 24);
        if (PFD && kb >= 2) {
#pragma unroll 1
          for (int j = kb == 2 ? 3 : kb + PFD; j <= kb + PFD && j < 16; j++) {
            if (lane < 16) asm volatile("prefetch.global.L2 [%0];" ::"l"(pfx + j * 128));
            if (lane < 24) asm volatile("prefetch.global.L2 [%0];" ::"l"(pfw + j * (64 * 6144)));
          }
          if (kb >= QPF && kb < QPF + 8) asm volatile("prefetch.global.L2 [%0];" ::"l"((const uint8_t*)P.q + (blockIdx.x * 256 + (kb - QPF) * 32 + lane) * 128));
          if (kb >= 4)
            asm volatile("prefetch.global.L2 [%0];" ::"l"(kb < 12 ? (const uint8_t*)P.h + (blockIdx.x * 256 + (kb - 4) * 32 + lane) * 128
                                                                  : (const uint8_t*)P.wo + (blockIdx.x * 128 + (kb - 12) * 32 + lane) * 128));
        }
        if (++st == 3) { st = 0; pp ^= 1; }
      }
      if (lane == 0) STAMP(2, 1);
    } else {
      {
        const uint32_t clk0 = __shfl_sync(~0u, (uint32_t)clock(), 0), stg = sb + OFF_STG + hw * STG_STRIDE;
        const unsigned epoch = __shfl_sync(~0u, P.epoch[blockIdx.x], 0);
        const uint32_t tag = ~epoch & 1;
        uint32_t tap[2][4];
#pragma unroll
        for (int cg = 0; cg < 2; cg++) {
          const uint2 u = __ldg((const uint2*)(P.shift_k + (16 * cl + 8 * cg + g) * 4));
          tap[cg][0] = __byte_perm(u.x, 0, 0x1010); tap[cg][1] = __byte_perm(u.x, 0, 0x3232);
          tap[cg][2] = __byte_perm(u.y, 0, 0x1010); tap[cg][3] = __byte_perm(u.y, 0, 0x3232);
        }
        if (hw == 0 && lane < 8) *(float*)(smem + OFF_D + 4 * lane) = __bfloat162float(P.D[blockIdx.x * 8 + lane]);
        if (hw == 1) asm volatile("prefetch.global.L2 [%0];" ::"l"(P.thr + (lane + 32 * (blockIdx.x & 1)) * 32));
        if (hw == 0 && elect_one()) {
          *(volatile unsigned*)(smem + OFF_EPOCH) = epoch;
          mbar_expect(BAR(B_XRAW), 16384);
          mbar_expect(BAR(B_Y), 16384 + 64);
        }
        for (int i = hw * 32 + lane; i < 528; i += 96) st_tag4(P.part + (hp * 8 + mb) * 2176 + 4 * i, 0.f, 0.f, 0.f, 0.f, tag ^ 1);
        if (hw < 2 || lane < 2) st_tag4(P.kv + hp * 2176 + (4 * (hw < 2 ? 64 * mb + 32 * hw + lane : 512 + 2 * mb + lane)), 0.f, 0.f, 0.f, 0.f, tag ^ 1);
        if (lane == 0) STAMP(3, hw);
        const uint32_t xo = sb + OFF_XT + g * XT_STRIDE + rank * 2048 + q * 4;
        const int krow = 8 + (lane & 7) - (lane >> 3);
        const uint32_t ka = stg + krow * 32 + ((krow & 4) << 2), va = stg + 2304 + lane * 32 + ((lane & 4) << 2);
        int ph = 0, b = 0;
#pragma unroll 1
        for (int ci = hw - 3; ci < 16; ci += 3) {
          const uint32_t bo = b ? OFF_F2F - OFF_STG : 0, bn = b ? 0 : OFF_F2F - OFF_STG;
          if (ci + 3 < 16) {
            while (__any_sync(~0u, (uint32_t)clock() - clk0 < HSTART + (ci + 3) * PACE)) __nanosleep(64);
            if (elect_one()) {
              mbar_expect(sbar + 8 * (b ^ 1), 2304 + 2048);
              tma2d(stg + bn, &P.tmK, 16 * cl, 1024 * rank + 64 * (ci + 3) - 8, sbar + 8 * (b ^ 1));
              tma2d(stg + bn + 2304, &P.tmV, 16 * cl, 1024 * rank + 64 * (ci + 3), sbar + 8 * (b ^ 1));
            }
          }
          if (ci >= 0) {
            mbar_wait(sbar + 8 * b, (ph >> b) & 1);
            ph ^= 1 << b;
#pragma unroll 1
            for (int grp = 0; grp < 2; grp++) {
#pragma unroll
              for (int cg = 0; cg < 2; cg++) {
                const uint32_t dst = mapa(xo + (ci >> 3) * 1024 + ((ci & 7) * 4 + 2 * grp) * 16, cg), xbar = mapa(BAR(B_XRAW), cg);
                uint32_t vv[4], kk[4][4];
                ldsm4t(vv, (va ^ (cg * 16)) + bo + grp * 1024);
#pragma unroll
                for (int rg = 0; rg < 4; rg++) ldsm4t(kk[rg], (ka ^ (cg * 16)) + bo + grp * 1024 + rg * 256);
#pragma unroll
                for (int rg = 0; rg < 4; rg++)
                  vv[rg] = hmul(hadd(hadd(hadd(hmul(kk[rg][3], tap[cg][3]), hmul(kk[rg][2], tap[cg][2])), hmul(kk[rg][1], tap[cg][1])), hmul(kk[rg][0], tap[cg][0])), vv[rg]);
                if (cg == rank) {
#pragma unroll
                  for (int rg = 0; rg < 4; rg++) asm volatile("st.shared.b32 [%0], %1;" ::"r"(dst + (rg & 1) * 512 + (rg >> 1) * 16), "r"(vv[rg]) : "memory");
                } else {
#pragma unroll
                  for (int rg = 0; rg < 4; rg++) st_async(dst + (rg & 1) * 512 + (rg >> 1) * 16, vv[rg], xbar);
                }
              }
            }
          }
          b ^= 1;
        }
      }
      if (lane == 0) STAMP(3, 3 + hw);
      asm volatile("bar.sync 4, 96;" ::: "memory");
      if (hw == 0 && elect_one()) { mbar_expect(BAR(B_XT), 10240); bulk_ld(sb + OFF_F2F, P.img, 10240, BAR(B_XT)); }
      mbar_wait(BAR(B_XRAW), 0);
    }
    int e1 = 0;
#pragma unroll 1
    for (int n = hw < 0 ? 3 : 0; n < 4; n++) {
      const bool isH = n >= 3;
      const int c = isH ? (warp & 1) + 2 * (warp & 2) : hw + 3 * n;
      if (c < 8) {
        int ln;
        asm volatile("mov.u32 %0, %%laneid;" : "=r"(ln));
        uint8_t* dst = smem + (isH ? OFF_H + (c & 2) * 8192 + (c >> 2) * 8192 + (c & 1) * 4096 : OFF_XT + c * XT_STRIDE) + ((ln >> 4) * 512 + (ln & 15) * 16);
        const uint8_t* src0 = isH ? (const uint8_t*)P.h + (blockIdx.x * 8 + c) * 4096 + ((ln & 15) * 32 + (ln & 16)) : dst;
        const uint8_t* src1 = src0 + (isH ? 512 : 256);
        uint32_t v[32];
#pragma unroll
        for (int i = 0; i < 8; i++) {
          const uint4 u = *(const uint4*)(((i & 1) ? src1 : src0) + (i >> 1) * 1024);
          v[4 * i] = u.x; v[4 * i + 1] = u.y; v[4 * i + 2] = u.z; v[4 * i + 3] = u.w;
        }
        if (isH) mbar_wait(BAR(B_XT), 0);
        const float f0 = __uint_as_float(v[0] << 16) + ((isH && ln == 0) ? *(const float*)(smem + OFF_D + 4 * c) : 0.f);
        const int e = norm_exp(v, f0);
        norm_cvt<0, 32>(v, f0, e);
        if (isH) mbar_wait(BAR(B_SFREE), 0);
        else if (ln == 0) smem[OFF_EX + c] = e;
        e1 = e;
#pragma unroll
        for (int i = 0; i < 8; i++)
          *(uint4*)(dst + (i >> 1) * 1024 + (i & 1) * 256) = make_uint4(v[4 * i], v[4 * i + 1], v[4 * i + 2], v[4 * i + 3]);
        if (n < 2 && elect_one()) {
          if (n == 0) mbar_expect(sbar, 4096);
          tma3d(sb + OFF_STG + 2048 * c, &P.tmQ, 16 * cl, 64 * rank, 2 * c, sbar);
        }
      }
      if (n >= 2) {
        fence_async();
        __syncwarp();
        if (lane == 0) { mbar_arrive(BAR(isH ? B_H : B_XT)); STAMP(3, (isH ? 17 : 13) + hw); }
      }
    }
#define SLOT(tab, kb) (sb + ((uint32_t)((tab) >> (4 * (kb))) & 15) * 16384)
#define LOAD_B(kb) tma4d(SLOT(SLOT_B, kb), &P.tmWo, 0, ((kb) >> 3) * 32, 2 * ((kb) & 7), 4 * cb + 2 * rank, BAR(B_FULL2 + (kb)))
#define LOAD_A(kb) bulk_ld_mc(SLOT(SLOT_A, kb) + rank * 8192, P.o + (rb * 16 + (kb)) * 1024 + rank * 512, 8192, BAR(B_FULL2 + (kb)))
    asm volatile("setmaxnreg.inc.sync.aligned.u32 104;");
    {
    int tid;
    asm volatile("mov.u32 %0, %%tid.x;" : "=r"(tid));
    const int lane = tid & 31, g = lane >> 2, q = lane & 3;
    const unsigned epoch = *(volatile unsigned*)(smem + OFF_EPOCH);
    const uint32_t tag = ~epoch & 1;
    const int pi = hw < 2 ? 64 * mb - 288 + tid : 512 + 2 * mb + (lane & 1);
    const float* psrc = P.part + hp * 8 * 2176 + 4 * pi;
    uint4 f[8];
    {
      const uint32_t s16 = (sb & 0x3FFFF) >> 4;
      const int t = tid & 127, c = 2 + (warp & 1) + 2 * (warp & 2);
      uint32_t v[32];
      const uint4* hp4 = (const uint4*)(P.h + (blockIdx.x * 8 + c) * 2048) + ((lane & 15) * 2 + (lane >> 4));
#pragma unroll
      for (int i = 0; i < 8; i++) { const uint4 u = ld_nc4(hp4 + i * 32); v[4 * i] = u.x; v[4 * i + 1] = u.y; v[4 * i + 2] = u.z; v[4 * i + 3] = u.w; }
      float kva[36];
#pragma unroll
      for (int mt = 0; mt < 2; mt++) {
        mbar_wait(BAR(B_PKRDY + mt), 0);
        wg_fence();
#pragma unroll
        for (int ks = 0; ks < 8; ks++) {
          const uint32_t o = (ks >> 2) * 1024 + mt * 512 + (ks & 3) * 128, vb = (2 * STAGE_BYTES >> 4) + o;
          wgmma_ss_n72<1, 1>(kva, dsc(s16 + o + (1 << 16), SW128), dsc(s16 + vb + (((OFF_ONES >> 4) - vb) << 16), SW128), (mt | ks) != 0);
        }
        wg_commit();
        if (BEARLY && mt == 0 && hw < 0) {
          mbar_wait(BAR(B_G1DONE), 0);
          if (elect_one()) {
#pragma unroll
            for (int kb = 0; kb < BEARLY; kb++) { mbar_expect(BAR(B_FULL2 + kb), 16384); LOAD_B(kb); }
          }
        }
      }
      float* pdst = P.part + (hp * 8 + mb) * 2176 + t * 4;
      float* zdst = P.part + (hp * 8 + mb) * 2176 + 2048 + (t >> 1);
      asm volatile("" : "+l"(pdst), "+l"(zdst));
      wg_wait<0>();
      keep(kva);
      if (hw < 1) {
#pragma unroll
        for (int c = 0; c < 4; c++) st_tag4(pdst + c * 512, kva[4 * c], kva[4 * c + 1], kva[4 * c + 2], kva[4 * c + 3], tag);
      } else {
#pragma unroll
        for (int c = 4; c < 8; c++) st_tag4(pdst + (c - 4) * 512, kva[4 * c], kva[4 * c + 1], kva[4 * c + 2], kva[4 * c + 3], tag);
      }
      const float z2 = __shfl_down_sync(~0u, kva[32], 4), z3 = __shfl_down_sync(~0u, kva[34], 4);
      if (!(lane & 7)) st_tag4(zdst, kva[32], kva[34], z2, z3, tag);
      if (lane == 0) mbar_arrive(BAR(B_PKFREE));
      const uint32_t cst = clock();
      if (hw == 0 && lane == 0) STAMP(3, 24);
      const float f0 = __uint_as_float(v[0] << 16) + (lane == 0 ? *(const float*)(smem + OFF_D + 4 * c) : 0.f);
      const int e = norm_exp(v, f0);
      if (HSPL > 0) norm_cvt<0, HSPL>(v, f0, e);
      if (hw >= 0) {
        while (__any_sync(~0u, (uint32_t)clock() - cst < PD1)) {}
        if (hw == 0 && lane == 0) STAMP(3, 20);
#pragma unroll
        for (int p = 0; p < 8; p++) f[p] = ld_rlx4(psrc + p * 2176);
      }
      if (HSPL < 32) norm_cvt<HSPL, 32>(v, f0, e);
      uint8_t* dst = smem + OFF_H + 16384 + (warp & 3) * 4096 + (lane >> 4) * 512 + (lane & 15) * 16;
#pragma unroll
      for (int i = 0; i < 8; i++)
        *(uint4*)(dst + (i >> 1) * 1024 + (i & 1) * 256) = make_uint4(v[4 * i], v[4 * i + 1], v[4 * i + 2], v[4 * i + 3]);
      if (lane < 4) {
        const int cc = c - (lane & 2);
        st_async(mapa(sb + OFF_SCALE + (8 * rank + cc) * 4, lane & 1), min(max(((lane & 2) ? e1 : e) + smem[OFF_EX + cc] - 124, 1), 254) << 23, mapa(BAR(B_Y), lane & 1));
      }
      fence_async();
      __syncwarp();
      if (lane == 0) mbar_arrive(BAR(B_H2));
    }
    if (warp == 8) {
      mbar_wait(BAR(B_PKFREE), 0);
      {
        const uint32_t c0 = clock();
#pragma unroll 1
        for (int i = 0; i < 14 - 2 * BEARLY; i++) {
          const int kb = (i >> 1) + BEARLY;
          while (__any_sync(~0u, (uint32_t)clock() - c0 < i * BPACE)) __nanosleep(32);
          if (elect_one()) {
            if (!(i & 1)) mbar_expect(BAR(B_FULL2 + kb), 16384);
            tma4d(SLOT(SLOT_B, kb) + (i & 1) * 8192, &P.tmWo1, 0, 0, 2 * kb, 4 * cb + 2 * rank + (i & 1), BAR(B_FULL2 + kb));
            if (i == 0) mbar_expect(BAR(B_Q), 8192);
            if (i < 4) tma3d(sb + OFF_SPARE + 2048 * i, &P.tmQ, 16 * cl, 64 * rank + 32 * (i >> 1), 2 * ((i + 6) & 7), BAR(B_Q));
          }
        }
      }
      if (lane == 0) STAMP(2, 2);
      mbar_wait(BAR(B_AFREE), 0);
      if (elect_one()) mbar_expect(BAR(B_FULL2), 16384);
      {
        const uint32_t dst = SLOT(SLOT_A, 0) + rank * 8192;
        const uint4* src = P.o + rb * 16 * 1024 + rank * 512;
        poll_ge(&P.ocnt[rb * 32], 16 * (epoch + 1));
        asm volatile("fence.proxy.async.global;" ::: "memory");
        if (lane == 0) STAMP(2, 3);
        if (elect_one()) bulk_ld_mc(dst, src, 8192, BAR(B_FULL2));
        if (lane == 0) STAMP(3, 23);
      }
#pragma unroll 1
      for (int kb = 1; kb < 7; kb++) {
        mbar_wait(BAR(kb < 3 ? B_AFREE + kb : B_CONS2 + ((kb - 3) >> 1)), 0);
        if (elect_one()) { mbar_expect(BAR(B_FULL2 + kb), 16384); LOAD_A(kb); }
      }
#pragma unroll 1
      for (int kb = 7; kb < 16; kb++) {
        mbar_wait(BAR(B_CONS2 + kb - 5), 0);
        if (kb == 8) mbar_wait(BAR(B_O1RDY), 0);
        if (elect_one()) { mbar_expect(BAR(B_FULL2 + kb), 32768); LOAD_A(kb); LOAD_B(kb); }
      }
      if (lane == 0) { P.epoch[blockIdx.x] = epoch + 1; STAMP(2, 5); }
    } else {
      {
#pragma unroll 1
        for (int n = 0; __any_sync(~0u, stale8(f, tag) & 1); n++) {
#pragma unroll
          for (int p = 0; p < 8; p++) ld_stale4(f[p], psrc + p * 2176, tag);
          if (n > SPIN_LIMIT) __trap();
        }
        float s0 = 0.f, s1 = 0.f, s2 = 0.f, s3 = 0.f;
#pragma unroll
        for (int p = 0; p < 8; p++) { s0 += __uint_as_float(f[p].x); s1 += __uint_as_float(f[p].y); s2 += __uint_as_float(f[p].z); s3 += __uint_as_float(f[p].w); }
        if (hw < 2 || lane < 2) st_tag4(P.kv + hp * 2176 + (4 * pi), s0, s1, s2, s3, tag);
      }
      if (lane == 0 && hw == 0) STAMP(3, 8);
      if (hw == 2) {
        unsigned* cnt = P.ocnt + (2 * mb + lane) * 32;
#pragma unroll 1
        for (int hh = 0; hh < 2; hh++) {
          mbar_wait(BAR(hh ? B_ODONE1 : B_ODONE), 0);
          if (lane < 2) asm volatile("red.release.gpu.global.add.u32 [%0], 1;" ::"l"(cnt + hh * 512) : "memory");
          if (lane == 0) STAMP(3, hh ? 6 : 7);
        }
        poll_ge(&P.ocnt[512 + rb * 32], 16 * (epoch + 1));
        asm volatile("fence.proxy.async.global;" ::: "memory");
        if (lane == 0) { mbar_arrive(BAR(B_O1RDY)); STAMP(2, 4); }
        __syncwarp();
      } else {
        if (PD2) __nanosleep(PD2);
        const int t = tid - 288;
        const float* src = P.kv + hp * 2176 + (4 * t);
        const float* zsrc = P.kv + hp * 2176 + (2048 + (t & 48) + 2 * (lane & 6));
        uint4 zp = ld_rlx4(zsrc);
#pragma unroll
        for (int p = 0; p < 8; p++) f[p] = ld_rlx4(src + 4 * ((p & 3) * 128 + (p >> 2) * 64));
        if (!opaque_true()) __trap();
#pragma unroll 1
        for (int n = 0; __any_sync(~0u, (stale8(f, tag) | (zp.x ^ tag)) & 1); n++) {
          ld_stale4(zp, zsrc, tag);
#pragma unroll
          for (int p = 0; p < 8; p++) ld_stale4(f[p], src + 4 * ((p & 3) * 128 + (p >> 2) * 64), tag);
          if (n > SPIN_LIMIT) __trap();
        }
#define PK2U(a, b) pk2(__uint_as_float(a), __uint_as_float(b))
        const uint32_t zf = (lane & 1) ? ((lane & 8) ? zp.w : zp.z) : ((lane & 8) ? zp.y : zp.x);
        const uint32_t zz = PK2U(zf, zf);
        *(uint4*)(smem + OFF_KVB + hw * 2560 + 2048 + lane * 16) = make_uint4(zz, zz, zz, zz);
        if (!opaque_true()) __trap();
#pragma unroll
        for (int hh = 0; hh < 2; hh++) {
          const uint4* ff = &f[4 * hh];
          uint8_t* dst = smem + OFF_KVB + hh * 2560 + q * 512 + (16 * hw + g) * 16;
          *(uint4*)dst = make_uint4(PK2U(ff[0].x, ff[0].y), PK2U(ff[1].x, ff[1].y), PK2U(ff[2].x, ff[2].y), PK2U(ff[3].x, ff[3].y));
          *(uint4*)(dst + 128) = make_uint4(PK2U(ff[0].z, ff[0].w), PK2U(ff[1].z, ff[1].w), PK2U(ff[2].z, ff[2].w), PK2U(ff[3].z, ff[3].w));
        }
        fence_async();
        __syncwarp();
        if (lane == 0) { mbar_arrive(BAR(B_KV)); if (hw == 0) STAMP(3, 9); }
      }
#define QBUF(ci) (sb + 2048 * (ci) + ((ci) < 6 ? OFF_STG : (ci) < 10 ? OFF_SPARE - 6 * 2048 : OFF_F2F - 10 * 2048))
      mbar_wait(BAR(B_Y), 0);
      if (elect_one()) {
        mbar_expect(sbar + 8, 4096);
#pragma unroll 1
        for (int ci = hw ? hw + 9 : 12; ci < 16; ci += 3) tma3d(QBUF(ci), &P.tmQ, 16 * cl, 64 * rank + 32, 2 * (ci & 7), sbar + 8);
      }
      mbar_wait(BAR(B_Q), 0);
      mbar_wait(sbar, hw == 0);
      {
        const float2 sc0 = *(const float2*)(smem + OFF_SCALE + 8 * q), sc1 = *(const float2*)(smem + OFF_SCALE + 32 + 8 * q);
        const uint32_t yl = sb + OFF_XT + (lane & 7) * XT_STRIDE + (lane >> 3) * 16;
#pragma unroll 1
        for (int ci = hw; ci < 16; ci += 3) {
          const uint32_t qb = QBUF(ci);
          if (ci >= 10) mbar_wait(sbar + 8, 1);
#pragma unroll 1
          for (int nl = 0; nl < 2; nl++) {
            uint32_t yy[2][4], qq[2][4];
            const uint32_t qa = qb + lane * 32 + ((lane & 4) << 2) + nl * 1024;
#pragma unroll
            for (int cg = 0; cg < 2; cg++) { ldsm4t(yy[cg], yl + cg * 2048 + (2 * ci + nl) * 64); ldsm4(qq[cg], qa ^ (cg * 16)); }
#pragma unroll
            for (int cg = 0; cg < 2; cg++) {
              const float2 sc = cg ? sc1 : sc0;
#pragma unroll
              for (int m = 0; m < 4; m++) {
                const float2 f = __half22float2(*(const __half2*)&yy[cg][m]);
                qq[cg][m] = hmul(qq[cg][m], pk2(f.x * sc.x, f.y * sc.y));
              }
              stsm4(qa ^ (cg * 16), qq[cg][0], qq[cg][1], qq[cg][2], qq[cg][3]);
            }
          }
          fence_async();
          __syncwarp();
          if (elect_one()) tma3d_st(&P.tmOA, qb, 16 * cl, 64 * rank + 32 * (ci >> 3), 2 * (ci & 7));
        }
        asm volatile("cp.async.bulk.commit_group;\ncp.async.bulk.wait_group.read 0;" ::: "memory");
      }
      if (lane == 0) STAMP(3, 10 + hw);
    }
    }
  }
}

typedef CUresult (*EncodeFn)(CUtensorMap*, CUtensorMapDataType, cuuint32_t, void*, const cuuint64_t*, const cuuint64_t*,
                             const cuuint32_t*, const cuuint32_t*, CUtensorMapInterleave, CUtensorMapSwizzle,
                             CUtensorMapL2promotion, CUtensorMapFloatOOBfill);

static void enc(EncodeFn fn, CUtensorMap* m, const void* p, int rank, const cuuint64_t* dims, const cuuint64_t* strides,
                const cuuint32_t* box, CUtensorMapSwizzle swz, CUtensorMapL2promotion promo) {
  cuuint32_t es[4] = {1, 1, 1, 1};
  fn(m, CU_TENSOR_MAP_DATA_TYPE_BFLOAT16, rank, (void*)p, dims, strides, box, es, CU_TENSOR_MAP_INTERLEAVE_NONE, swz, promo,
     CU_TENSOR_MAP_FLOAT_OOB_FILL_NONE);
}

extern "C" void kernel_launch(void* const* d_in, const int* in_sizes, int n_in, void* d_out, int out_size) {
  void* fp = nullptr;
  cudaDriverEntryPointQueryResult qr;
  cudaGetDriverEntryPoint("cuTensorMapEncodeTiled", &fp, cudaEnableDefault, &qr);
  EncodeFn fn = (EncodeFn)fp;
  Params P;
  P.shift_k = (const __nv_bfloat16*)d_in[3]; P.h = (const __nv_bfloat16*)d_in[4]; P.D = (const __nv_bfloat16*)d_in[5];
  P.q = (const __nv_bfloat16*)d_in[0];
  cudaGetSymbolAddress((void**)&P.part, g_part); cudaGetSymbolAddress((void**)&P.kv, g_kv); cudaGetSymbolAddress((void**)&P.o, g_o);
  cudaGetSymbolAddress((void**)&P.ocnt, g_ocnt); cudaGetSymbolAddress((void**)&P.epoch, g_epoch);
  cudaGetSymbolAddress((void**)&P.thr, c_thr); cudaGetSymbolAddress((void**)&P.img, c_img);
  P.x = (const __nv_bfloat16*)d_in[6]; P.w = (const __nv_bfloat16*)d_in[7]; P.wo = (const __nv_bfloat16*)d_in[8];
  const CUtensorMapSwizzle S128 = CU_TENSOR_MAP_SWIZZLE_128B, S32 = CU_TENSOR_MAP_SWIZZLE_32B;
  const CUtensorMapL2promotion P0 = CU_TENSOR_MAP_L2_PROMOTION_NONE, P128 = CU_TENSOR_MAP_L2_PROMOTION_L2_128B;
  { cuuint64_t d[2] = {1024, 2048}, s[1] = {2048}; cuuint32_t b[2] = {64, 128}; enc(fn, &P.tmX, d_in[6], 2, d, s, b, S128, P128); }
  { cuuint64_t d[3] = {1024, 1024, 3}, s[2] = {6144, 2048}; cuuint32_t b[3] = {64, 64, 3}; enc(fn, &P.tmW, d_in[7], 3, d, s, b, S128, P128); }
  { cuuint64_t d[4] = {64, 64, 16, 16}, s[3] = {2048, 131072, 128}; cuuint32_t b[4] = {64, 32, 2, 2}; enc(fn, &P.tmWo, d_in[8], 4, d, s, b, S128, P128); }
  { cuuint64_t d[4] = {64, 64, 16, 16}, s[3] = {2048, 131072, 128}; cuuint32_t b[4] = {64, 32, 2, 1}; enc(fn, &P.tmWo1, d_in[8], 4, d, s, b, S128, P128); }
  { cuuint64_t d[2] = {1024, 2048}, s[1] = {2048}; cuuint32_t b[2] = {16, 72}; enc(fn, &P.tmK, d_in[1], 2, d, s, b, S32, PKV); }
  { cuuint64_t d[2] = {1024, 2048}, s[1] = {2048}; cuuint32_t b[2] = {16, 64}; enc(fn, &P.tmV, d_in[2], 2, d, s, b, S32, PKV); }
  { cuuint64_t d[3] = {1024, 128, 16}, s[2] = {32768, 2048}; cuuint32_t b[3] = {16, 32, 2}; enc(fn, &P.tmQ, d_in[0], 3, d, s, b, S32, PKV); }
  { cuuint64_t d[3] = {1024, 128, 16}, s[2] = {65536, 4096}; cuuint32_t b[3] = {16, 32, 2}; enc(fn, &P.tmOA, d_out, 3, d, s, b, S32, P0); }
  { cuuint64_t d[2] = {2048, 2048}, s[1] = {4096}; cuuint32_t b[2] = {64, 16}; enc(fn, &P.tmOB, d_out, 2, d, s, b, S128, P0); }
  cudaFuncSetAttribute(fused_kernel, cudaFuncAttributeMaxDynamicSharedMemorySize, SMEM_TOTAL);
  fused_kernel<<<128, 384, SMEM_TOTAL>>>(P);
}
```

```cpp
#include <cuda_runtime.h>
#include <cuda_bf16.h>
#include <cuda_fp16.h>
#include <cuda.h>
#include <stdint.h>

template<int TA, int TB, int SA=1> __device__ __forceinline__ void wgmma_ss_n192(float (&d)[96], uint64_t da, uint64_t db, int scale_d) {
  asm volatile("{\n.reg .pred p;\nsetp.ne.b32 p, %98, 0;\n"
    "wgmma.mma_async.sync.aligned.m64n192k16.f32.bf16.bf16 {%0, %1, %2, %3, %4, %5, %6, %7, %8, %9, %10, %11, %12, %13, %14, %15, %16, %17, %18, %19, %20, %21, %22, %23, %24, %25, %26, %27, %28, %29, %30, %31, %32, %33, %34, %35, %36, %37, %38, %39, %40, %41, %42, %43, %44, %45, %46, %47, %48, %49, %50, %51, %52, %53, %54, %55, %56, %57, %58, %59, %60, %61, %62, %63, %64, %65, %66, %67, %68, %69, %70, %71, %72, %73, %74, %75, %76, %77, %78, %79, %80, %81, %82, %83, %84, %85, %86, %87, %88, %89, %90, %91, %92, %93, %94, %95}, %96, %97, p, %101, 1, %99, %100;\n}\n"
    : "+f"(d[0]), "+f"(d[1]), "+f"(d[2]), "+f"(d[3]), "+f"(d[4]), "+f"(d[5]), "+f"(d[6]), "+f"(d[7]), "+f"(d[8]), "+f"(d[9]), "+f"(d[10]), "+f"(d[11]), "+f"(d[12]), "+f"(d[13]), "+f"(d[14]), "+f"(d[15]), "+f"(d[16]), "+f"(d[17]), "+f"(d[18]), "+f"(d[19]), "+f"(d[20]), "+f"(d[21]), "+f"(d[22]), "+f"(d[23]), "+f"(d[24]), "+f"(d[25]), "+f"(d[26]), "+f"(d[27]), "+f"(d[28]), "+f"(d[29]), "+f"(d[30]), "+f"(d[31]), "+f"(d[32]), "+f"(d[33]), "+f"(d[34]), "+f"(d[35]), "+f"(d[36]), "+f"(d[37]), "+f"(d[38]), "+f"(d[39]), "+f"(d[40]), "+f"(d[41]), "+f"(d[42]), "+f"(d[43]), "+f"(d[44]), "+f"(d[45]), "+f"(d[46]), "+f"(d[47]), "+f"(d[48]), "+f"(d[49]), "+f"(d[50]), "+f"(d[51]), "+f"(d[52]), "+f"(d[53]), "+f"(d[54]), "+f"(d[55]), "+f"(d[56]), "+f"(d[57]), "+f"(d[58]), "+f"(d[59]), "+f"(d[60]), "+f"(d[61]), "+f"(d[62]), "+f"(d[63]), "+f"(d[64]), "+f"(d[65]), "+f"(d[66]), "+f"(d[67]), "+f"(d[68]), "+f"(d[69]), "+f"(d[70]), "+f"(d[71]), "+f"(d[72]), "+f"(d[73]), "+f"(d[74]), "+f"(d[75]), "+f"(d[76]), "+f"(d[77]), "+f"(d[78]), "+f"(d[79]), "+f"(d[80]), "+f"(d[81]), "+f"(d[82]), "+f"(d[83]), "+f"(d[84]), "+f"(d[85]), "+f"(d[86]), "+f"(d[87]), "+f"(d[88]), "+f"(d[89]), "+f"(d[90]), "+f"(d[91]), "+f"(d[92]), "+f"(d[93]), "+f"(d[94]), "+f"(d[95])
    : "l"(da), "l"(db), "r"(scale_d), "n"(TA), "n"(TB), "n"(SA));
}
template<int TA, int TB, int SA=1> __device__ __forceinline__ void wgmma_ss_n128(float (&d)[64], uint64_t da, uint64_t db, int scale_d) {
  asm volatile("{\n.reg .pred p;\nsetp.ne.b32 p, %66, 0;\n"
    "wgmma.mma_async.sync.aligned.m64n128k16.f32.bf16.bf16 {%0, %1, %2, %3, %4, %5, %6, %7, %8, %9, %10, %11, %12, %13, %14, %15, %16, %17, %18, %19, %20, %21, %22, %23, %24, %25, %26, %27, %28, %29, %30, %31, %32, %33, %34, %35, %36, %37, %38, %39, %40, %41, %42, %43, %44, %45, %46, %47, %48, %49, %50, %51, %52, %53, %54, %55, %56, %57, %58, %59, %60, %61, %62, %63}, %64, %65, p, %69, 1, %67, %68;\n}\n"
    : "+f"(d[0]), "+f"(d[1]), "+f"(d[2]), "+f"(d[3]), "+f"(d[4]), "+f"(d[5]), "+f"(d[6]), "+f"(d[7]), "+f"(d[8]), "+f"(d[9]), "+f"(d[10]), "+f"(d[11]), "+f"(d[12]), "+f"(d[13]), "+f"(d[14]), "+f"(d[15]), "+f"(d[16]), "+f"(d[17]), "+f"(d[18]), "+f"(d[19]), "+f"(d[20]), "+f"(d[21]), "+f"(d[22]), "+f"(d[23]), "+f"(d[24]), "+f"(d[25]), "+f"(d[26]), "+f"(d[27]), "+f"(d[28]), "+f"(d[29]), "+f"(d[30]), "+f"(d[31]), "+f"(d[32]), "+f"(d[33]), "+f"(d[34]), "+f"(d[35]), "+f"(d[36]), "+f"(d[37]), "+f"(d[38]), "+f"(d[39]), "+f"(d[40]), "+f"(d[41]), "+f"(d[42]), "+f"(d[43]), "+f"(d[44]), "+f"(d[45]), "+f"(d[46]), "+f"(d[47]), "+f"(d[48]), "+f"(d[49]), "+f"(d[50]), "+f"(d[51]), "+f"(d[52]), "+f"(d[53]), "+f"(d[54]), "+f"(d[55]), "+f"(d[56]), "+f"(d[57]), "+f"(d[58]), "+f"(d[59]), "+f"(d[60]), "+f"(d[61]), "+f"(d[62]), "+f"(d[63])
    : "l"(da), "l"(db), "r"(scale_d), "n"(TA), "n"(TB), "n"(SA));
}
template<int TA, int TB, int SA=1> __device__ __forceinline__ void wgmma_ss_n72(float (&d)[36], uint64_t da, uint64_t db, int scale_d) {
  asm volatile("{\n.reg .pred p;\nsetp.ne.b32 p, %38, 0;\n"
    "wgmma.mma_async.sync.aligned.m64n72k16.f32.bf16.bf16 {%0, %1, %2, %3, %4, %5, %6, %7, %8, %9, %10, %11, %12, %13, %14, %15, %16, %17, %18, %19, %20, %21, %22, %23, %24, %25, %26, %27, %28, %29, %30, %31, %32, %33, %34, %35}, %36, %37, p, %41, 1, %39, %40;\n}\n"
    : "+f"(d[0]), "+f"(d[1]), "+f"(d[2]), "+f"(d[3]), "+f"(d[4]), "+f"(d[5]), "+f"(d[6]), "+f"(d[7]), "+f"(d[8]), "+f"(d[9]), "+f"(d[10]), "+f"(d[11]), "+f"(d[12]), "+f"(d[13]), "+f"(d[14]), "+f"(d[15]), "+f"(d[16]), "+f"(d[17]), "+f"(d[18]), "+f"(d[19]), "+f"(d[20]), "+f"(d[21]), "+f"(d[22]), "+f"(d[23]), "+f"(d[24]), "+f"(d[25]), "+f"(d[26]), "+f"(d[27]), "+f"(d[28]), "+f"(d[29]), "+f"(d[30]), "+f"(d[31]), "+f"(d[32]), "+f"(d[33]), "+f"(d[34]), "+f"(d[35])
    : "l"(da), "l"(db), "r"(scale_d), "n"(TA), "n"(TB), "n"(SA));
}
template<int TB, int SA=1> __device__ __forceinline__ void wgmma_rs_n40(float (&d)[20], uint32_t a0, uint32_t a1, uint32_t a2, uint32_t a3, uint64_t db, int scale_d) {
  asm volatile("{\n.reg .pred p;\nsetp.ne.b32 p, %25, 0;\n"
    "wgmma.mma_async.sync.aligned.m64n40k16.f32.bf16.bf16 {%0, %1, %2, %3, %4, %5, %6, %7, %8, %9, %10, %11, %12, %13, %14, %15, %16, %17, %18, %19}, {%20, %21, %22, %23}, %24, p, %27, 1, %26;\n}\n"
    : "+f"(d[0]), "+f"(d[1]), "+f"(d[2]), "+f"(d[3]), "+f"(d[4]), "+f"(d[5]), "+f"(d[6]), "+f"(d[7]), "+f"(d[8]), "+f"(d[9]), "+f"(d[10]), "+f"(d[11]), "+f"(d[12]), "+f"(d[13]), "+f"(d[14]), "+f"(d[15]), "+f"(d[16]), "+f"(d[17]), "+f"(d[18]), "+f"(d[19])
    : "r"(a0), "r"(a1), "r"(a2), "r"(a3), "l"(db), "r"(scale_d), "n"(TB), "n"(SA));
}
template<int TB> __device__ __forceinline__ void wgmma_hrs_n64(uint32_t (&d)[16], uint32_t a0, uint32_t a1, uint32_t a2, uint32_t a3, uint64_t db, int scale_d) {
  asm volatile("{\n.reg .pred p;\nsetp.ne.b32 p, %21, 0;\n"
    "wgmma.mma_async.sync.aligned.m64n64k16.f16.f16.f16 {%0, %1, %2, %3, %4, %5, %6, %7, %8, %9, %10, %11, %12, %13, %14, %15}, {%16, %17, %18, %19}, %20, p, 1, 1, %22;\n}\n"
    : "+r"(d[0]), "+r"(d[1]), "+r"(d[2]), "+r"(d[3]), "+r"(d[4]), "+r"(d[5]), "+r"(d[6]), "+r"(d[7]), "+r"(d[8]), "+r"(d[9]), "+r"(d[10]), "+r"(d[11]), "+r"(d[12]), "+r"(d[13]), "+r"(d[14]), "+r"(d[15])
    : "r"(a0), "r"(a1), "r"(a2), "r"(a3), "l"(db), "r"(scale_d), "n"(TB));
}
template<int TB> __device__ __forceinline__ void wgmma_hrs_n32(uint32_t (&d)[8], uint32_t a0, uint32_t a1, uint32_t a2, uint32_t a3, uint64_t db, int scale_d) {
  asm volatile("{\n.reg .pred p;\nsetp.ne.b32 p, %13, 0;\n"
    "wgmma.mma_async.sync.aligned.m64n32k16.f16.f16.f16 {%0, %1, %2, %3, %4, %5, %6, %7}, {%8, %9, %10, %11}, %12, p, 1, 1, %14;\n}\n"
    : "+r"(d[0]), "+r"(d[1]), "+r"(d[2]), "+r"(d[3]), "+r"(d[4]), "+r"(d[5]), "+r"(d[6]), "+r"(d[7])
    : "r"(a0), "r"(a1), "r"(a2), "r"(a3), "l"(db), "r"(scale_d), "n"(TB));
}

__device__ __align__(128) const uint32_t c_thr[1536] = {
  0x33fb33ff,0xa49c9de4,0x33273352,0xaf2cae76,0x33e233f1,0xa96ca7bd,0x32c432f7,0xb045afdd,0x33b733cf,0xac3eaaf7,0x3250328c,0xb0eab099,
  0x3378339a,0xadbcacff,0x31cd3211,0xb182b137,0x33d033fb,0xaadea46a,0x299e2d17,0xb3e0b396,0x32fb337a,0xafd2adb1,0xa78b1f76,0xb3f2b3ff,
  0x318b3254,0xb1c5b0e5,0xae6bac32,0xb354b3b8,0x2f4230a3,0xb321b285,0xb133b040,0xb215b2c7,0x337c33f2,0xada5a759,0xb179afc8,0xb1d6b2fe,
  0x31463293,0xb204b08e,0xb394b2ba,0xad23b055,0x2b402f4e,0xb3cbb31e,0xb3e4b3f9,0x293ba533,0xac269c52,0xb3bab400,0xb258b357,0x30e02e5f,
  0x330133e5,0xafbda922,0xb3f3b3c9,0x2727ab59,0x2deb314a,0xb36fb200,0xb194b32f,0x31bc2f0a,0xacdb2084,0xb39fb3ff,0xa565aea4,0x33f93347,
  0xb2b6b0db,0xb05ab25c,0x30892c1a,0x329733bc,0x326033d4,0xb0d6aa94,0xb00ab29b,0x32e83084,0x20e82f64,0xb3feb318,0x2d8da597,0x338133f8,
  0xb1fcae48,0xb14fb35c,0x339031b8,0x2d3a3199,0xb3e6b3ae,0x2909ac7b,0x32d133f4,0xb030a6f5,0x319d33bf,0xb1b3ac02,0x2e3ca874,0x335e33ec,
  0xacc32b89,0xb3a3b3c6,0x33f83276,0x25c930b7,0xb3dcb1f8,0xaa01b154,0x30653335,0xb2b0aef4,0xb107b383,0x32392d81,0xafa6214d,0xb307b3fe,
  0x30bc33a5,0xb273acb7,0x33c5311b,0x2ba23229,0xb0cc94b6,0xb267b400,0x30153360,0xb2e1ae31,0xb385b3ab,0x2d76ac93,0xb166a691,0xb1e7b3f5,
  0x22deb06a,0x33fd32ac,0xb337b3da,0x2ee8aa19,0x2f853387,0xb310ad6a,0x322d33fe,0xb1162216,0xb2a9abd3,0xb06fb3c2,0xb07428a6,0xb2a5b3ea,
  0xb111b3e9,0x323128be,0xb30db3c3,0x2f90abba,0x31aa227a,0x31a633fd,0x2e25ad5e,0x33633389,0x2d6a3365,0xb387ae1a,0xa21631aa,0xb3feb1a6,
  0xb3c2af85,0xabd3b310,0xb3eab22d,0x28a6b116,0xa8beb2a9,0x33e9306f,0x2bbab074,0x33c332a5,0x33fd3111,0x227a3231,0x3389330d,0xad5e2f90,
  0x2a63333f,0xb3d7aec6,0xb2a2a1b1,0xb07ab3fe,0xb3f7b158,0x25fbb1f4,0xacb7b38b,0x33a52d52,0x2e0eb025,0x336832d8,0x340030bc,0x14b63273,
  0x323533c0,0xb10c2beb,0xac9330cc,0xb3abb267,0x23433316,0xb3fdaf6f,0xb38eb225,0x2d46b11f,0xb342b29e,0x2ebbb07f,0x31e3aa7c,0x316b33d6,
  0x3264a6c3,0x30d133f5,0x2c0233ac,0xb3bfac87,0x28f0336a,0xb3e7ae02,0xb3c6b19d,0x2b89b1b3,0xa59732e8,0xb3f8b00a,0xaccfb3ed,0x33a1285b,
  0xb1b8b381,0x3199ad8d,0x336c31df,0xadf73170,0x33f42d3a,0x26f53390,0xb30423a7,0xafb2b3fc,0xb05f3030,0xb2b3b2d1,0x29e8b27a,0x33dd30b2,
  0xab5932b6,0xb3c9b05a,0x30adb089,0x327e3297,0xaf0ab3f3,0x332fa727,0x240633b0,0xb3fcac6f,0x33473194,0xaea431bc,0xb174b359,0x31daae54,
  0xb3bca565,0xac1ab3f9,0x33ee2f59,0xa842331b,0xaddf3281,0xb371b0a8,0x34002b40,0x1c5233cb,0xa759b3ef,0x33f22829,0xb2fe2c26,0xafc8b3ba,
  0x308e337c,0xb2932da5,0x3055b179,0x32ba31d6,0xb31eb146,0x2f4eb204,0xa5333394,0xb3f9ad23,0xaff33249,0xb2f1b0f3,0x30e532fb,0xb2542fd2,
  0x2b28b373,0x33cc2dd4,0xb285b18b,0x30a3b1c5,0x246a33fa,0xb3fba500,0x33962f42,0xad173321,0xadb1b3d0,0x337aaade,0xb3ffa99e,0x1f76b3e0,
  0xb0ee320d,0xb24db13c,0xac4b3398,0xb3b5ad0b,0x304ab289,0x32c1309e,0x2985b3ce,0x33e12b0f,0xaf3732f4,0xb324afe8,0xa4ce33f0,0xb3faa7ef,
  0x2dc8b34f,0x33762e82,0x9de4b3ff,0x33ff1ead,0xb1c931cd,0xb186b182,0xb3762e82,0xadc8b34f,0x324db13c,0x30ee320d,0x33b5ad0b,0x2c4b3398,
  0xb2c1309e,0xb04ab289,0xb3e12b0f,0xa985b3ce,0x3324afe8,0x2f3732f4,0x33faa7ef,0x24ce33f0,0xb285318b,0xb0a3b1c5,0xb2c7ae6b,0x3040b354,
  0x3396af42,0x2d173321,0x31413133,0xb2093215,0xb3ff299e,0x9f76b3e0,0xae8db2bd,0x334cb050,0x33b8278b,0xac3233f2,0x281033b3,0xb3ef2c57,
  0xb31e3146,0xaf4eb204,0xa533b394,0x33f9ad23,0x3400ab40,0x9c5233cb,0xae5f33e4,0xb357a93b,0xb2feac26,0x2fc8b3ba,0x3245b258,0x30f830e0,
  0x30553179,0xb2ba31d6,0xb3df2e99,0xa9b6b34a,0xb39230fd,0xad2fb241,0x3200b301,0x314a2fbd,0x337f1b11,0xad993400,0xb3ff2deb,0xa084b36f,
  0xb005b129,0x32ebb21d,0x325c2cdb,0xb0db339f,0xa92233de,0xb3e529cf,0xab59b2b6,0x33c9b05a,0xb3dd30b2,0xa9e8b27a,0x33d4ab71,0xaa9433c8,
  0x32212c0e,0xb12433bd,0xaf64b0d6,0x3318b260,0x197fb345,0x3400aeaf,0xae4833fe,0xb35c20e8,0xb23d3332,0xb102aeff,0x33aeb14f,0x2c7b31fc,
  0xb3fe3065,0xa14db2b0,0x2ebb307f,0xb342329e,0x300f2fa6,0xb2e53307,0x30d1b3f5,0x326426c3,0x302ab400,0x32d517db,0xb3e72e02,0x28f0b36a,
  0xb3fd2f6f,0x2343b316,0x2d46311f,0xb38e3225,0xb3f53015,0x2691b2e1,0xaf9b33eb,0xb30a288d,0x2a193166,0xb3da31e7,0x33d7aec6,0xaa63333f,
  0x3313b337,0x2f7a2ee8,0xa5fbb1f4,0x33f7b158,0xb1a1a8d7,0x31afb3e8,0xb36832d8,0xae0eb025,0xb3c22f85,0x2bd3b310,0xb3ea322d,0xa8a6b116,
  0xa8be32a9,0xb3e9306f,0x2bba3074,0xb3c332a5,0x33fdb111,0xa27a3231,0x3389b30d,0x2d5e2f90,0xa216b1aa,0x33feb1a6,0xaed2ae25,0x333db363,
  0xb3652edd,0x2e1ab33a,0xb1aa227a,0x31a6b3fd,0xaf853387,0xb3102d6a,0xb22d33fe,0xb116a216,0x32a9abd3,0xb06f33c2,0x307428a6,0xb2a533ea,
  0x3111b3e9,0x3231a8be,0x330db3c3,0x2f902bba,0xb2e12e31,0x3015b360,0x288db1a1,0x33ebb1af,0xb1e733f5,0xb1662691,0xb33f2f9b,0x2ec6b30a,
  0x2ee82a19,0xb33733da,0xb15833d7,0xb1f42a63,0x33e8b313,0x28d72f7a,0x302525fb,0xb2d833f7,0xb2392d81,0x3107b383,0x3307b3fe,0x2fa6214d,
  0xb35e33ec,0xae3ca874,0x97dbb00f,0x3400b2e5,0xa5c930b7,0xb3f83276,0xb316302a,0x2f6fb2d5,0x32b0aef4,0xb0653335,0xb29e33fd,0xb07f2343,
  0xb1702ccf,0x31dfb3a1,0x3345b124,0xaeaf3221,0xb3fc336c,0xa3a7adf7,0x3332b400,0x2eff997f,0xb0b23304,0xb27a2fb2,0x2b71b102,0x33c8b23d,
  0x2c0e29e8,0xb3bd33dd,0xb0d62a94,0x3260b3d4,0xb0892c1a,0x3297b3bc,0x2aad2842,0xb3d333ee,0xb3b0327e,0x2c6fb0ad,0x3241b035,0xb0fd32ce,
  0xb35933fc,0xae542406,0x3400b392,0x1b112d2f,0xaf5931da,0xb31b3174,0x321db37f,0x3129ad99,0xaf152ac6,0x332cb3d2,0xb1463293,0xb204308e,
  0xb281312e,0x30a8b219,0xab402f4e,0xb3cb331e,0xb3ef3371,0x2829addf,0x2c269c52,0xb3ba3400,0xb37c33f2,0xada52759,0x3179afc8,0xb1d632fe,
  0xacf32953,0x339cb3e3,0xb3fa33cc,0x2500ab28,0xb0942f21,0x3290b32a,0xb3d033fb,0xaade246a,0xb249317d,0x30f3b1d2,0xb2fb337a,0xafd22db1,
  0xb37332f1,0x2dd4aff3,0xb18b3254,0xb1c530e5,0xa96c27bd,0x33e2b3f1,0xb0452fdd,0x32c4b2f7,0xac3e2af7,0x33b7b3cf,0xb0ea3099,0x3250b28c,
  0xadbc2cff,0x3378b39a,0xb1823137,0x31cdb211,0xaf2c2e76,0x3327b352,0xb20d31c9,0x313cb186,0x313c3186,0xb20db1c9,0x2d0b2dc8,0xb398b376,
  0x309e30ee,0xb289b24d,0x2b0f2c4b,0xb3ceb3b5,0x2fe8304a,0xb2f4b2c1,0x27ef2985,0xb3f0b3e1,0x2e822f37,0xb34fb324,0x1ead24ce,0xb3ffb3fa,
  0xb2bdb209,0xb050b141,0xb290b32a,0x30942f21,0xb3b3b34c,0xac57ae8d,0xb0f3b1d2,0x3249317d,0xb400b3ef,0x1d1ba810,0xadd4aff3,0x337332f1,
  0xb39cb3e3,0x2cf32953,0xa500ab28,0x33fa33cc,0xae99b0f8,0x334a3245,0x33ff33b2,0x201f2c63,0x2438a9b6,0x33fc33df,0x332c33d2,0xaf15aac6,
  0x303a2ce7,0x32cb339e,0x30a83219,0xb281b12e,0x32ee31c0,0x2ffe3190,0x28292ddf,0xb3efb371,0x33b0327e,0x2c6f30ad,0xb241b035,0xb0fdb2ce,
  0x335933fc,0xae54a406,0xb400b392,0x1b11ad2f,0x2f5931da,0xb31bb174,0xb21db37f,0x31292d99,0xaaad2842,0xb3d3b3ee,0xa9cfb005,0x33de32eb,
  0x285b305f,0xb3edb2b3,0x2c0ea9e8,0x33bd33dd,0xb170accf,0xb1dfb3a1,0x33453124,0x2eaf3221,0xb3fcb36c,0x23a7adf7,0x33323400,0xaeff997f,
  0xb0b2b304,0x327a2fb2,0x2b713102,0xb3c8b23d,0xb400b2e5,0x17dbb00f,0x2e023264,0xb36ab0d1,0xaf6fb2d5,0x3316302a,0xb11fa8f0,0xb225b3e7,
  0x307f2343,0x329e33fd,0xb3d6b38e,0x2a7cad46,0x33f53342,0xa6c32ebb,0xac87b1e3,0x33ac316b,0x28d7af7a,0x33e83313,0xb2d8b3f7,0x3025a5fb,
  0x33eb31af,0x288d31a1,0x2bebae0e,0x33c03368,0x2ec6330a,0xb33faf9b,0x33fe3235,0x21b1310c,0xb1f4aa63,0xb158b3d7,0x2d5232a2,0xb38bb07a,
  0x33a7333d,0xacab2ed2,0x33f63162,0x262d31eb,0xaa4b301a,0xb3d8b2de,0x2a32326b,0xb3d9b0c7,0xb3f6b26f,0x265fb0c1,0xb3a9b020,0xac9fb2db,
  0x0e48b15d,0x340031f0,0xae1ab33a,0x33652edd,0xaed22e25,0xb33db363,0xb1eb0e48,0xb162b400,0xb2deb3a7,0x301aacab,0xb0c7b3f6,0x326b262d,
  0x30c1aa4b,0x326f33d8,0x32db2a32,0x302033d9,0x31f033f6,0xb15d265f,0x2edd33a9,0xb33aac9f,0xb2acb385,0x306aad76,0x2a19b166,0x33da31e7,
  0x3229a2de,0x311b33fd,0x33133337,0xaf7a2ee8,0x2e3133c5,0xb360aba2,0xb1a128d7,0xb1afb3e8,0xb3f5b015,0xa691b2e1,0xaf9bb3eb,0x330a288d,
  0x3154acc3,0x31f833a3,0x2ef433f8,0xb335a5c9,0x2d8133dc,0xb383aa01,0xb3feb065,0x214db2b0,0xb3ecb107,0x2874b239,0x300fafa6,0x32e53307,
  0x30b7ae3c,0x3276335e,0x302a3400,0xb2d517db,0x312433bd,0xb2212c0e,0xb318b260,0x2f64b0d6,0xb400aeaf,0x997fb345,0x335c20e8,0x2e4833fe,
  0x3102aeff,0x323d3332,0xac7b31fc,0xb3aeb14f,0x2a9433c8,0xb3d4ab71,0xb084b3e6,0x329ba909,0xb2ce2aad,0xb035b3d3,0x33e529cf,0x292233de,
  0x2d2fb241,0x339230fd,0xb14a2fbd,0xb200b301,0x2d993400,0xb37f1b11,0x2084b36f,0x33ff2deb,0xb2ebb21d,0x3005b129,0x30db339f,0xb25c2cdb,
  0xae5fb3e4,0x3357a93b,0xb190303a,0xb1c0b2cb,0x32453258,0xb0f830e0,0x2c63b2ee,0x33b22ffe,0xb3dfae99,0x29b6b34a,0x2ac633ff,0xb3d2a01f,
  0x339ea438,0x2ce733fc,0xb12eb32c,0x3219af15,0x33b8a78b,0x2c3233f2,0x2810b3b3,0x33ef2c57,0xb2c72e6b,0xb040b354,0x29533400,0xb3e31d1b,
  0x3141b133,0x32093215,0xaf21b39c,0x332aacf3,0xae8d32bd,0xb34cb050,0x317d3290,0xb1d23094,0x27bd33fb,0xb3f1249c,0x2fdd3327,0xb2f72f2c,
  0xaaf7b3e2,0x33cfa96c,0xb099b2c4,0x328cb045,0x2cff33b7,0xb39a2c3e,0x31373250,0xb21130ea,0xae76b378,0x3352adbc,0xb1c9b1cd,0x3186b182,
  0xb3ff1ead,0x1de4b3ff,0xb352adbc,0x2e76b378,0x33f1249c,0xa7bd33fb,0x32f72f2c,0xafdd3327,0xb3cfa96c,0x2af7b3e2,0xb28cb045,0x3099b2c4,
  0x339a2c3e,0xacff33b7,0x321130ea,0xb1373250,0x2953b400,0x33e31d1b,0x33ccadd4,0x2b283373,0xaf21339c,0xb32aacf3,0xb3fb2500,0x246ab3fa,
  0x317db290,0x31d23094,0x337a2ade,0xadb133d0,0xb2f130f3,0xaff3b249,0xb254afd2,0x30e5b2fb,0x339e2438,0xace733fc,0xb12e332c,0xb219af15,
  0xb190b03a,0x31c0b2cb,0x3371b0a8,0x2ddf3281,0x2c6332ee,0xb3b22ffe,0xb3f22829,0x2759b3ef,0x2ac6b3ff,0x33d2a01f,0x32932da5,0xb08e337c,
  0xaf0a33f3,0xb32fa727,0x2406b3b0,0x33fcac6f,0x3347b194,0x2ea431bc,0xb1743359,0xb1daae54,0xb3bc2565,0x2c1ab3f9,0x33eeaf59,0x2842331b,
  0x30ad3089,0xb27e3297,0xb2ceaaad,0x3035b3d3,0xb29ba909,0x3084b3e6,0x305f3030,0xb2b332d1,0x259732e8,0xb3f8300a,0x2ccfb3ed,0x33a1a85b,
  0x31b8b381,0x31992d8d,0xb36c31df,0xadf7b170,0xb3f42d3a,0x26f5b390,0x330423a7,0xafb233fc,0x316bb3d6,0x31e32a7c,0xb3832a01,0x2d81b3dc,
  0xb3bf2c87,0x2c02b3ac,0x28743239,0xb3ec3107,0x2b8931b3,0xb3c6319d,0x3276b35e,0x30b72e3c,0x31f8b3a3,0x31542cc3,0xb33525c9,0x2ef4b3f8,
  0x310c2beb,0xb23533c0,0x33abb267,0x2c9330cc,0x307ab3fe,0x32a2a1b1,0xb06aad76,0x32acb385,0xb3a52d52,0x2cb7b38b,0xb11b33fd,0xb229a2de,
  0x94b63273,0xb40030bc,0x3360aba2,0xae3133c5,0xb2de33a7,0xb01aacab,0xb0c733f6,0xb26b262d,0x30c12a4b,0xb26f33d8,0x32dbaa32,0xb02033d9,
  0x31f0b3f6,0x315d265f,0x2eddb3a9,0x333aac9f,0xb1eb8e48,0x3162b400,0xb3872e1a,0x2d6ab365,0xae25ad5e,0x3363b389,0x8e48b15d,0x3400b1f0,
  0xb3a7333d,0xacabaed2,0xb3f63162,0x262db1eb,0x2a4b301a,0xb3d832de,0xaa32326b,0xb3d930c7,0x33f6b26f,0x265f30c1,0x33a9b020,0xac9f32db,
  0x33c0b368,0x2beb2e0e,0x30cc94b6,0xb2673400,0x21b1b10c,0x33feb235,0x3385b3ab,0x2d762c93,0xb38b307a,0x2d52b2a2,0xa2deb06a,0x33fdb2ac,
  0xb0bc33a5,0xb2732cb7,0xb3c5311b,0x2ba2b229,0x26c32ebb,0xb3f53342,0xb3ac316b,0x2c87b1e3,0x336ab0d1,0xae023264,0xb19d33bf,0xb1b32c02,
  0x3225b3e7,0x311fa8f0,0x2cc32b89,0xb3a333c6,0xaa7cad46,0x33d6b38e,0x33dcb1f8,0xaa013154,0xb3fe3318,0x20e8af64,0x3381b3f8,0x2d8d2597,
  0xb14f335c,0xb1fc2e48,0x2d3ab199,0x3390b1b8,0x29092c7b,0xb3e633ae,0xb03026f5,0x32d1b3f4,0x32e8b084,0xb00a329b,0xb3ed32b3,0x285bb05f,
  0x29cfb005,0x33deb2eb,0xb05a325c,0xb2b630db,0xafbd2922,0x3301b3e5,0x27272b59,0xb3f333c9,0xb36f3200,0x2debb14a,0x31bcaf0a,0xb194332f,
  0xb39f33ff,0xacdba084,0x33f9b347,0xa5652ea4,0x3394b2ba,0xad233055,0xa438a9b6,0x33fcb3df,0x33e4b3f9,0x293b2533,0xb03a2ce7,0x32cbb39e,
  0x3258b357,0x30e0ae5f,0xb2ee31c0,0x2ffeb190,0x2e99b0f8,0x334ab245,0xb3ff33b2,0x201fac63,0xaf4230a3,0xb3213285,0x3133b040,0xb21532c7,
  0xa99e2d17,0xb3e03396,0x32bdb209,0xb0503141,0x278b1f76,0xb3f233ff,0x33b3b34c,0xac572e8d,0x2e6bac32,0xb35433b8,0x3400b3ef,0x1d1b2810,
  0xb289324d,0x309eb0ee,0xb3ce33b5,0x2b0fac4b,0xb2f432c1,0x2fe8b04a,0xb3f033e1,0x27efa985,0xb34f3324,0x2e82af37,0xb3ff33fa,0x1eada4ce,
  0xb3983376,0x2d0badc8,0xb3fb33ff,0xa49c1de4,0x351c35f6,0xac93a617,0xb8a3b93c,0x308d2a16,0x32f43448,0xb160afa5,0xb6a4b7fe,0x353a3389,
  0x2fa53160,0xb448b2f4,0xb389b53a,0x37fe36a4,0x26172c93,0xb5f6b51c,0xaa16b08d,0x393c38a3,0x34c3358c,0xac47a5b2,0xb85fb8f3,0x304229b1,
  0x327e33fd,0xb106af26,0xb63cb785,0x34e7330f,0x2f263106,0xb3fdb27e,0xb30fb4e7,0x3785363c,0x25b22c47,0xb58cb4c3,0xa9b1b042,0x38f3385f,
  0x346a3523,0xabf6a54d,0xb81ab8a8,0x2fef294d,0x3209336b,0xb0acaea7,0xb5d4b70a,0x34933294,0x2ea730ac,0xb36bb209,0xb294b493,0x370a35d4,
  0x254d2bf6,0xb523b46a,0xa94dafef,0x38a8381a,0x341334bc,0xab5fa4e9,0xb7a6b85a,0x2f5928e8,0x319432da,0xb052ae28,0xb56ab68d,0x343e3219,
  0x2e283052,0xb2dab194,0xb219b43e,0x368d356a,0x24e92b5f,0xb4bcb413,0xa8e8af59,0x385a37a6,0x33783456,0xaac8a484,0xb715b80a,0x2ec32884,
  0x3120324a,0xaff2ada9,0xb4ffb60e,0x33d3319e,0x2da92ff2,0xb24ab120,0xb19eb3d3,0x360e34ff,0x24842ac8,0xb456b378,0xa884aec3,0x380a3715,
  0x32cd33e3,0xaa31a420,0xb682b76f,0x2e2d281f,0x30ac31bb,0xaf3fad2a,0xb493b58d,0x33283122,0x2d2a2f3f,0xb1bbb0ac,0xb122b328,0x358d3493,
  0x24202a31,0xb3e3b2cd,0xa81fae2d,0x376f3682,0x3223331c,0xa999a376,0xb5ebb6c6,0x2d972776,0x3039312d,0xae8dacac,0xb426b50b,0x327c30a6,
  0x2cac2e8d,0xb12db039,0xb0a6b27c,0x350b3426,0x23762999,0xb31cb223,0xa776ad97,0x36c635eb,0x317a3257,0xa902a2ad,0xb552b61a,0x2d0026ad,
  0x2f8c309f,0xaddcac2e,0xb371b487,0x31cf3029,0x2c2e2ddc,0xb09faf8c,0xb029b1cf,0x34873371,0x22ad2902,0xb257b17a,0xa6adad00,0x361a3552,
  0x30d23194,0xa86ba1e4,0xb4b7b56a,0x2c6a25e4,0x2ea73012,0xad2aab5f,0xb294b402,0x31222f59,0x2b5f2d2a,0xb012aea7,0xaf59b122,0x34023294,
  0x21e4286b,0xb194b0d2,0xa5e4ac6a,0x356a34b7,0x302c30d2,0xa7a9a11b,0xb41ab4b7,0x2ba7251b,0x2dc22f0c,0xac79aa63,0xb1b6b2f7,0x30742e5f,
  0x2a632c79,0xaf0cadc2,0xae5fb074,0x32f731b6,0x211b27a9,0xb0d2b02c,0xa51baba7,0x34b7341a,0x2f0c3012,0xa67ba052,0xb2f7b402,0x2a7a2452,
  0x2cde2df5,0xab91a967,0xb0d7b1e8,0x2f8b2d65,0x29672b91,0xadf5acde,0xad65af8b,0x31e830d7,0x2052267b,0xb012af0c,0xa452aa7a,0x340232f7,
  0x2dc22ea7,0xa54d9f12,0xb1b6b294,0x294d2311,0x2bf62cde,0xaa31a86b,0xafefb0d7,0x2e2d2c6a,0x286b2a31,0xacdeabf6,0xac6aae2d,0x30d72fef,
  0x1f12254d,0xaea7adc2,0xa311a94d,0x329431b6,0x2c792d2a,0xa4209d7f,0xb074b122,0x281f217f,0x2a312b91,0xa8d0a6e0,0xae2daf8b,0x2cce2ade,
  0x26e028d0,0xab91aa31,0xaadeacce,0x2f8b2e2d,0x1d7f2420,0xad2aac79,0xa17fa81f,0x31223074,0x2a632b5f,0xa1e49bdb,0xae5faf59,0x25e41fdb,
  0x286b2967,0xa6e0a4e9,0xac6aad65,0x2ade28e8,0x24e926e0,0xa967a86b,0xa8e8aade,0x2d652c6a,0x1bdb21e4,0xab5faa63,0x9fdba5e4,0x2f592e5f,
  0x27a9286b,0x9f1298b6,0xaba7ac6a,0x23111cb6,0x254d267b,0xa420a1e4,0xa94daa7a,0x281f25e4,0x21e42420,0xa67ba54d,0xa5e4a81f,0x2a7a294d,
  0x18b61f12,0xa86ba7a9,0x9cb6a311,0x2c6a2ba7,0x211b21e4,0x98b69248,0xa51ba5e4,0x1cb61648,0x1f122052,0x9d7f9bdb,0xa311a452,0x217f1fdb,
  0x1bdb1d7f,0xa0529f12,0x9fdba17f,0x24522311,0x124818b6,0xa1e4a11b,0x96489cb6,0x25e4251b,0xa11ba1e4,0x18b61248,0x251b25e4,0x9cb69648,
  0x9f12a052,0x1d7f1bdb,0x23112452,0xa17f9fdb,0x9bdb9d7f,0x20521f12,0x1fdb217f,0xa452a311,0x924898b6,0x21e4211b,0x16481cb6,0xa5e4a51b,
  0xa7a9a86b,0x1f1218b6,0x2ba72c6a,0xa3119cb6,0xa54da67b,0x242021e4,0x294d2a7a,0xa81fa5e4,0xa1e4a420,0x267b254d,0x25e4281f,0xaa7aa94d,
  0x98b69f12,0x286b27a9,0x1cb62311,0xac6aaba7,0xaa63ab5f,0x21e41bdb,0x2e5f2f59,0xa5e49fdb,0xa86ba967,0x26e024e9,0x2c6a2d65,0xaadea8e8,
  0xa4e9a6e0,0x2967286b,0x28e82ade,0xad65ac6a,0x9bdba1e4,0x2b5f2a63,0x1fdb25e4,0xaf59ae5f,0xac79ad2a,0x24201d7f,0x30743122,0xa81fa17f,
  0xaa31ab91,0x28d026e0,0x2e2d2f8b,0xacceaade,0xa6e0a8d0,0x2b912a31,0x2ade2cce,0xaf8bae2d,0x9d7fa420,0x2d2a2c79,0x217f281f,0xb122b074,
  0xadc2aea7,0x254d1f12,0x31b63294,0xa94da311,0xabf6acde,0x2a31286b,0x2fef30d7,0xae2dac6a,0xa86baa31,0x2cde2bf6,0x2c6a2e2d,0xb0d7afef,
  0x9f12a54d,0x2ea72dc2,0x2311294d,0xb294b1b6,0xaf0cb012,0x267b2052,0x32f73402,0xaa7aa452,0xacdeadf5,0x2b912967,0x30d731e8,0xaf8bad65,
  0xa967ab91,0x2df52cde,0x2d652f8b,0xb1e8b0d7,0xa052a67b,0x30122f0c,0x24522a7a,0xb402b2f7,0xb02cb0d2,0x27a9211b,0x341a34b7,0xaba7a51b,
  0xadc2af0c,0x2c792a63,0x31b632f7,0xb074ae5f,0xaa63ac79,0x2f0c2dc2,0x2e5f3074,0xb2f7b1b6,0xa11ba7a9,0x30d2302c,0x251b2ba7,0xb4b7b41a,
  0xb0d2b194,0x286b21e4,0x34b7356a,0xac6aa5e4,0xaea7b012,0x2d2a2b5f,0x32943402,0xb122af59,0xab5fad2a,0x30122ea7,0x2f593122,0xb402b294,
  0xa1e4a86b,0x319430d2,0x25e42c6a,0xb56ab4b7,0xb17ab257,0x290222ad,0x3552361a,0xad00a6ad,0xaf8cb09f,0x2ddc2c2e,0x33713487,0xb1cfb029,
  0xac2eaddc,0x309f2f8c,0x302931cf,0xb487b371,0xa2ada902,0x3257317a,0x26ad2d00,0xb61ab552,0xb223b31c,0x29992376,0x35eb36c6,0xad97a776,
  0xb039b12d,0x2e8d2cac,0x3426350b,0xb27cb0a6,0xacacae8d,0x312d3039,0x30a6327c,0xb50bb426,0xa376a999,0x331c3223,0x27762d97,0xb6c6b5eb,
  0xb2cdb3e3,0x2a312420,0x3682376f,0xae2da81f,0xb0acb1bb,0x2f3f2d2a,0x3493358d,0xb328b122,0xad2aaf3f,0x31bb30ac,0x31223328,0xb58db493,
  0xa420aa31,0x33e332cd,0x281f2e2d,0xb76fb682,0xb378b456,0x2ac82484,0x3715380a,0xaec3a884,0xb120b24a,0x2ff22da9,0x34ff360e,0xb3d3b19e,
  0xada9aff2,0x324a3120,0x319e33d3,0xb60eb4ff,0xa484aac8,0x34563378,0x28842ec3,0xb80ab715,0xb413b4bc,0x2b5f24e9,0x37a6385a,0xaf59a8e8,
  0xb194b2da,0x30522e28,0x356a368d,0xb43eb219,0xae28b052,0x32da3194,0x3219343e,0xb68db56a,0xa4e9ab5f,0x34bc3413,0x28e82f59,0xb85ab7a6,
  0xb46ab523,0x2bf6254d,0x381a38a8,0xafefa94d,0xb209b36b,0x30ac2ea7,0x35d4370a,0xb493b294,0xaea7b0ac,0x336b3209,0x32943493,0xb70ab5d4,
  0xa54dabf6,0x3523346a,0x294d2fef,0xb8a8b81a,0xb4c3b58c,0x2c4725b2,0x385f38f3,0xb042a9b1,0xb27eb3fd,0x31062f26,0x363c3785,0xb4e7b30f,
  0xaf26b106,0x33fd327e,0x330f34e7,0xb785b63c,0xa5b2ac47,0x358c34c3,0x29b13042,0xb8f3b85f,0xb51cb5f6,0x2c932617,0x38a3393c,0xb08daa16,
  0xb2f4b448,0x31602fa5,0x36a437fe,0xb53ab389,0xafa5b160,0x344832f4,0x3389353a,0xb7feb6a4,0xa617ac93,0x35f6351c,0x2a16308d,0xb93cb8a3,
};
__device__ __align__(128) const uint32_t c_img[2560] = {
  0x326d31ed,0x333b32dd,0x33c33388,0x33fe33ea,0x33c331ed,0x31ed33c3,0xa8b22d64,0xb33bb0c4,0x33ea31ed,0xad64301d,0xb2ddb388,0x315fa8b2,
  0x32dd31ed,0xb3feabc6,0x326dad64,0xad64326d,0x30c431ed,0xaed7b2dd,0x2bc63388,0xa248b3ea,0x2bc631ed,0x315fb3c3,0xb3ea2d64,0x2ed730c4,
  0xa8b231ed,0x3388b01d,0x301db388,0xb1ed28b2,0xb01d31ed,0x22482bc6,0x30c4ad64,0x3388b26d,0x33ea33fe,0x338833c3,0x32dd333b,0x31ed326d,
  0xb2ddb3fe,0xa248b01d,0x326d2ed7,0x338833ea,0x30c433fe,0xb33babc6,0xabc6b33b,0x33fe30c4,0xabc6b3fe,0x31ed32dd,0xb3eaaed7,0x333ba8b2,
  0xa8b233fe,0x2d64b3c3,0xb01d333b,0x315fb26d,0x301db3fe,0xb3fe301d,0x30c42ed7,0x2d64b3ea,0xb26d33fe,0x2ed72bc6,0x33c3b33b,0xa248b0c4,
  0x33c3b3fe,0x315fb2dd,0x28b2aed7,0xaed728b2,0xb0c4b15f,0xaed7b01d,0xabc6ad64,0xa248a8b2,0xabc6b15f,0x315f2bc6,0x33ea3388,0x2ed7326d,
  0x28b2b15f,0x338832dd,0xb01d2d64,0xb1edb3ea,0x301db15f,0x224833c3,0xb0c4b388,0x338830c4,0x326db15f,0xb33b301d,0x33c3ad64,0xb3fe28b2,
  0x33c3b15f,0xb1edabc6,0xa8b23388,0x333bb26d,0x33eab15f,0x2d64b2dd,0xb2dd2d64,0xb15f33ea,0x32ddb15f,0x33feb3c3,0x326db388,0x2d64b0c4,
  0x28b22248,0x2d642bc6,0x301d2ed7,0x315f30c4,0xb01da248,0xb3feb2dd,0xb0c4b33b,0x2d64a8b2,0x326d2248,0x2ed733c3,0xb3c3aed7,0xa248b26d,
  0xb3c3a248,0x315fb01d,0xa8b2333b,0xaed7b3ea,0x33ea2248,0xb388abc6,0x32dd2ed7,0xb1edb0c4,0xb2dda248,0x224832dd,0x326db33b,0xb38828b2,
  0x30c42248,0x333bb3c3,0xabc6aed7,0xb3fe326d,0xabc6a248,0xb1ed301d,0xb3ea333b,0xb33b33ea,0xb26d31ed,0xb33b32dd,0xb3c33388,0xb3fe33ea,
  0xb3c331ed,0xb1ed33c3,0x28b22d64,0x333bb0c4,0xb3ea31ed,0x2d64301d,0x32ddb388,0xb15fa8b2,0xb2dd31ed,0x33feabc6,0xb26dad64,0x2d64326d,
  0xb0c431ed,0x2ed7b2dd,0xabc63388,0x2248b3ea,0xabc631ed,0xb15fb3c3,0x33ea2d64,0xaed730c4,0x28b231ed,0xb388b01d,0xb01db388,0x31ed28b2,
  0x301d31ed,0xa2482bc6,0xb0c4ad64,0xb388b26d,0xb3ea33fe,0xb38833c3,0xb2dd333b,0xb1ed326d,0x32ddb3fe,0x2248b01d,0xb26d2ed7,0xb38833ea,
  0xb0c433fe,0x333babc6,0x2bc6b33b,0xb3fe30c4,0x2bc6b3fe,0xb1ed32dd,0x33eaaed7,0xb33ba8b2,0x28b233fe,0xad64b3c3,0x301d333b,0xb15fb26d,
  0xb01db3fe,0x33fe301d,0xb0c42ed7,0xad64b3ea,0x326d33fe,0xaed72bc6,0xb3c3b33b,0x2248b0c4,0xb3c3b3fe,0xb15fb2dd,0xa8b2aed7,0x2ed728b2,
  0x30c4b15f,0x2ed7b01d,0x2bc6ad64,0x2248a8b2,0x2bc6b15f,0xb15f2bc6,0xb3ea3388,0xaed7326d,0xa8b2b15f,0xb38832dd,0x301d2d64,0x31edb3ea,
  0xb01db15f,0xa24833c3,0x30c4b388,0xb38830c4,0xb26db15f,0x333b301d,0xb3c3ad64,0x33fe28b2,0xb3c3b15f,0x31edabc6,0x28b23388,0xb33bb26d,
  0xb3eab15f,0xad64b2dd,0x32dd2d64,0x315f33ea,0xb2ddb15f,0xb3feb3c3,0xb26db388,0xad64b0c4,0xa8b22248,0xad642bc6,0xb01d2ed7,0xb15f30c4,
  0x301da248,0x33feb2dd,0x30c4b33b,0xad64a8b2,0xb26d2248,0xaed733c3,0x33c3aed7,0x2248b26d,0x33c3a248,0xb15fb01d,0x28b2333b,0x2ed7b3ea,
  0xb3ea2248,0x3388abc6,0xb2dd2ed7,0x31edb0c4,0x32dda248,0xa24832dd,0xb26db33b,0x338828b2,0xb0c42248,0xb33bb3c3,0x2bc6aed7,0x33fe326d,
  0x2bc6a248,0x31ed301d,0x33ea333b,0x333b33ea,0x30c4315f,0x2ed7301d,0x2bc62d64,0x224828b2,0x2bc6315f,0xb15fabc6,0xb3eab388,0xaed7b26d,
  0xa8b2315f,0xb388b2dd,0x301dad64,0x31ed33ea,0xb01d315f,0xa248b3c3,0x30c43388,0xb388b0c4,0xb26d315f,0x333bb01d,0xb3c32d64,0x33fea8b2,
  0xb3c3315f,0x31ed2bc6,0x28b2b388,0xb33b326d,0xb3ea315f,0xad6432dd,0x32ddad64,0x315fb3ea,0xb2dd315f,0xb3fe33c3,0xb26d3388,0xad6430c4,
  0xa8b2a248,0xad64abc6,0xb01daed7,0xb15fb0c4,0x301d2248,0x33fe32dd,0x30c4333b,0xad6428b2,0xb26da248,0xaed7b3c3,0x33c32ed7,0x2248326d,
  0x33c32248,0xb15f301d,0x28b2b33b,0x2ed733ea,0xb3eaa248,0x33882bc6,0xb2ddaed7,0x31ed30c4,0x32dd2248,0xa248b2dd,0xb26d333b,0x3388a8b2,
  0xb0c4a248,0xb33b33c3,0x2bc62ed7,0x33feb26d,0x2bc62248,0x31edb01d,0x33eab33b,0x333bb3ea,0x326d31ed,0x333b32dd,0x33c33388,0x33fe33ea,
  0x33c331ed,0x31ed33c3,0xa8b22d64,0xb33bb0c4,0x33ea31ed,0xad64301d,0xb2ddb388,0x315fa8b2,0x32dd31ed,0xb3feabc6,0x326dad64,0xad64326d,
  0x30c431ed,0xaed7b2dd,0x2bc63388,0xa248b3ea,0x2bc631ed,0x315fb3c3,0xb3ea2d64,0x2ed730c4,0xa8b231ed,0x3388b01d,0x301db388,0xb1ed28b2,
  0xb01d31ed,0x22482bc6,0x30c4ad64,0x3388b26d,0x33ea33fe,0x338833c3,0x32dd333b,0x31ed326d,0xb2ddb3fe,0xa248b01d,0x326d2ed7,0x338833ea,
  0x30c433fe,0xb33babc6,0xabc6b33b,0x33fe30c4,0xabc6b3fe,0x31ed32dd,0xb3eaaed7,0x333ba8b2,0xa8b233fe,0x2d64b3c3,0xb01d333b,0x315fb26d,
  0x301db3fe,0xb3fe301d,0x30c42ed7,0x2d64b3ea,0xb26d33fe,0x2ed72bc6,0x33c3b33b,0xa248b0c4,0x33c3b3fe,0x315fb2dd,0x28b2aed7,0xaed728b2,
  0xb0c4315f,0xaed7301d,0xabc62d64,0xa24828b2,0xabc6315f,0x315fabc6,0x33eab388,0x2ed7b26d,0x28b2315f,0x3388b2dd,0xb01dad64,0xb1ed33ea,
  0x301d315f,0x2248b3c3,0xb0c43388,0x3388b0c4,0x326d315f,0xb33bb01d,0x33c32d64,0xb3fea8b2,0x33c3315f,0xb1ed2bc6,0xa8b2b388,0x333b326d,
  0x33ea315f,0x2d6432dd,0xb2ddad64,0xb15fb3ea,0x32dd315f,0x33fe33c3,0x326d3388,0x2d6430c4,0x28b2a248,0x2d64abc6,0x301daed7,0x315fb0c4,
  0xb01d2248,0xb3fe32dd,0xb0c4333b,0x2d6428b2,0x326da248,0x2ed7b3c3,0xb3c32ed7,0xa248326d,0xb3c32248,0x315f301d,0xa8b2b33b,0xaed733ea,
  0x33eaa248,0xb3882bc6,0x32ddaed7,0xb1ed30c4,0xb2dd2248,0x2248b2dd,0x326d333b,0xb388a8b2,0x30c4a248,0x333b33c3,0xabc62ed7,0xb3feb26d,
  0xabc62248,0xb1edb01d,0xb3eab33b,0xb33bb3ea,0xb26d31ed,0xb33b32dd,0xb3c33388,0xb3fe33ea,0xb3c331ed,0xb1ed33c3,0x28b22d64,0x333bb0c4,
  0xb3ea31ed,0x2d64301d,0x32ddb388,0xb15fa8b2,0xb2dd31ed,0x33feabc6,0xb26dad64,0x2d64326d,0xb0c431ed,0x2ed7b2dd,0xabc63388,0x2248b3ea,
  0xabc631ed,0xb15fb3c3,0x33ea2d64,0xaed730c4,0x28b231ed,0xb388b01d,0xb01db388,0x31ed28b2,0x301d31ed,0xa2482bc6,0xb0c4ad64,0xb388b26d,
  0xb3ea33fe,0xb38833c3,0xb2dd333b,0xb1ed326d,0x32ddb3fe,0x2248b01d,0xb26d2ed7,0xb38833ea,0xb0c433fe,0x333babc6,0x2bc6b33b,0xb3fe30c4,
  0x2bc6b3fe,0xb1ed32dd,0x33eaaed7,0xb33ba8b2,0x28b233fe,0xad64b3c3,0x301d333b,0xb15fb26d,0xb01db3fe,0x33fe301d,0xb0c42ed7,0xad64b3ea,
  0x326d33fe,0xaed72bc6,0xb3c3b33b,0x2248b0c4,0xb3c3b3fe,0xb15fb2dd,0xa8b2aed7,0x2ed728b2,0x29ed29ed,0x29ed29ed,0x29ed29ed,0x29ed29ed,
  0x2bc32a6d,0x2add2bea,0x23c628c4,0xa81da0b2,0x2bc32add,0xa3c6281d,0xabc3aadd,0x23c6a81d,0x29ed2b3b,0xabfea564,0x295fa6d7,0x1a482b88,
  0x25642b88,0xa564ab88,0x25642b88,0xa564ab88,0xa0b22bc3,0x2a6daadd,0xabea23c6,0x28c4281d,0xa8c42bea,0x2a6da0b2,0x28c4abea,0xaa6d20b2,
  0xab3b2bfe,0xa564295f,0x26d79a48,0x2b88a9ed,0x29ed29ed,0x29ed29ed,0x29ed29ed,0x29ed29ed,0xabc3aa6d,0xaaddabea,0xa3c6a8c4,0x281d20b2,
  0x2bc32add,0xa3c6281d,0xabc3aadd,0x23c6a81d,0xa9edab3b,0x2bfe2564,0xa95f26d7,0x9a48ab88,0x25642b88,0xa564ab88,0x25642b88,0xa564ab88,
  0x20b2abc3,0xaa6d2add,0x2beaa3c6,0xa8c4a81d,0xa8c42bea,0x2a6da0b2,0x28c4abea,0xaa6d20b2,0x2b3babfe,0x2564a95f,0xa6d71a48,0xab8829ed,
  0x295f295f,0x295f295f,0x295f295f,0x295f295f,0x23c628c4,0xa81da0b2,0xabc3aa6d,0xaaddabea,0xa3c6281d,0xabc3aadd,0x23c6a81d,0x2bc32add,
  0xa95f26d7,0x9a48ab88,0x29ed2b3b,0xabfea564,0xab882564,0x2b88a564,0xab882564,0x2b88a564,0xabea23c6,0x28c4281d,0x20b2abc3,0xaa6d2add,
  0xaa6d20b2,0xa8c42bea,0x2a6da0b2,0x28c4abea,0xa6d71a48,0xab8829ed,0xab3b2bfe,0xa564295f,0x295f295f,0x295f295f,0x295f295f,0x295f295f,
  0xa3c6a8c4,0x281d20b2,0x2bc32a6d,0x2add2bea,0xa3c6281d,0xabc3aadd,0x23c6a81d,0x2bc32add,0x295fa6d7,0x1a482b88,0xa9edab3b,0x2bfe2564,
  0xab882564,0x2b88a564,0xab882564,0x2b88a564,0x2beaa3c6,0xa8c4a81d,0xa0b22bc3,0x2a6daadd,0xaa6d20b2,0xa8c42bea,0x2a6da0b2,0x28c4abea,
  0x26d79a48,0x2b88a9ed,0x2b3babfe,0x2564a95f,0xabfe2bfe,0xabfe2bfe,0xabfe2bfe,0xabfe2bfe,0xaadd2bea,0xa3c628c4,0x281da0b2,0x2bc3aa6d,
  0xa81d2bc3,0x2adda3c6,0x281dabc3,0xaadd23c6,0x9a482b88,0x29edab3b,0xabfe2564,0x295f26d7,0x26d72b3b,0xa6d7ab3b,0x26d72b3b,0xa6d7ab3b,
  0x2a6d2add,0xabeaa3c6,0x28c4a81d,0x20b22bc3,0x2bea2a6d,0xa0b228c4,0xabeaaa6d,0x20b2a8c4,0x2b8829ed,0x2b3b2bfe,0x2564295f,0xa6d79a48,
  0xabfe2bfe,0xabfe2bfe,0xabfe2bfe,0xabfe2bfe,0x2addabea,0x23c6a8c4,0xa81d20b2,0xabc32a6d,0xa81d2bc3,0x2adda3c6,0x281dabc3,0xaadd23c6,
  0x1a48ab88,0xa9ed2b3b,0x2bfea564,0xa95fa6d7,0x26d72b3b,0xa6d7ab3b,0x26d72b3b,0xa6d7ab3b,0xaa6daadd,0x2bea23c6,0xa8c4281d,0xa0b2abc3,
  0x2bea2a6d,0xa0b228c4,0xabeaaa6d,0x20b2a8c4,0xab88a9ed,0xab3babfe,0xa564a95f,0x26d71a48,0x1a489a48,0x1a489a48,0x1a489a48,0x1a489a48,
  0x281da0b2,0x2bc3aa6d,0x2addabea,0x23c6a8c4,0x2adda3c6,0x281dabc3,0xaadd23c6,0xa81d2bc3,0x2bfea564,0xa95fa6d7,0x9a482b88,0x29edab3b,
  0x2b3ba6d7,0xab3b26d7,0x2b3ba6d7,0xab3b26d7,0x28c4a81d,0x20b22bc3,0xaa6daadd,0x2bea23c6,0x20b2a8c4,0x2bea2a6d,0xa0b228c4,0xabeaaa6d,
  0xa564a95f,0x26d71a48,0x2b8829ed,0x2b3b2bfe,0x1a489a48,0x1a489a48,0x1a489a48,0x1a489a48,0xa81d20b2,0xabc32a6d,0xaadd2bea,0xa3c628c4,
  0x2adda3c6,0x281dabc3,0xaadd23c6,0xa81d2bc3,0xabfe2564,0x295f26d7,0x1a48ab88,0xa9ed2b3b,0x2b3ba6d7,0xab3b26d7,0x2b3ba6d7,0xab3b26d7,
  0xa8c4281d,0xa0b2abc3,0x2a6d2add,0xabeaa3c6,0x20b2a8c4,0x2bea2a6d,0xa0b228c4,0xabeaaa6d,0x2564295f,0xa6d79a48,0xab88a9ed,0xab3babfe,
  0xa95fa95f,0xa95fa95f,0xa95fa95f,0xa95fa95f,0xa3c6a8c4,0x281d20b2,0x2bc32a6d,0x2add2bea,0x23c6a81d,0x2bc32add,0xa3c6281d,0xabc3aadd,
  0x295fa6d7,0x1a482b88,0xa9edab3b,0x2bfe2564,0x2b88a564,0xab882564,0x2b88a564,0xab882564,0x2beaa3c6,0xa8c4a81d,0xa0b22bc3,0x2a6daadd,
  0x2a6da0b2,0x28c4abea,0xaa6d20b2,0xa8c42bea,0x26d79a48,0x2b88a9ed,0x2b3babfe,0x2564a95f,0xa95fa95f,0xa95fa95f,0xa95fa95f,0xa95fa95f,
  0x23c628c4,0xa81da0b2,0xabc3aa6d,0xaaddabea,0x23c6a81d,0x2bc32add,0xa3c6281d,0xabc3aadd,0xa95f26d7,0x9a48ab88,0x29ed2b3b,0xabfea564,
  0x2b88a564,0xab882564,0x2b88a564,0xab882564,0xabea23c6,0x28c4281d,0x20b2abc3,0xaa6d2add,0x2a6da0b2,0x28c4abea,0xaa6d20b2,0xa8c42bea,
  0xa6d71a48,0xab8829ed,0xab3b2bfe,0xa564295f,0x29ed29ed,0x29ed29ed,0x29ed29ed,0x29ed29ed,0x2bc32a6d,0x2add2bea,0x23c628c4,0xa81da0b2,
  0x2bc32add,0xa3c6281d,0xabc3aadd,0x23c6a81d,0x29ed2b3b,0xabfea564,0x295fa6d7,0x1a482b88,0x25642b88,0xa564ab88,0x25642b88,0xa564ab88,
  0xa0b22bc3,0x2a6daadd,0xabea23c6,0x28c4281d,0xa8c42bea,0x2a6da0b2,0x28c4abea,0xaa6d20b2,0xab3b2bfe,0xa564295f,0x26d79a48,0x2b88a9ed,
  0x29ed29ed,0x29ed29ed,0x29ed29ed,0x29ed29ed,0xabc3aa6d,0xaaddabea,0xa3c6a8c4,0x281d20b2,0x2bc32add,0xa3c6281d,0xabc3aadd,0x23c6a81d,
  0xa9edab3b,0x2bfe2564,0xa95f26d7,0x9a48ab88,0x25642b88,0xa564ab88,0x25642b88,0xa564ab88,0x20b2abc3,0xaa6d2add,0x2beaa3c6,0xa8c4a81d,
  0xa8c42bea,0x2a6da0b2,0x28c4abea,0xaa6d20b2,0x2b3babfe,0x2564a95f,0xa6d71a48,0xab8829ed,0x9a481a48,0x9a481a48,0x9a481a48,0x9a481a48,
  0xa81d20b2,0xabc32a6d,0xaadd2bea,0xa3c628c4,0xaadd23c6,0xa81d2bc3,0x2adda3c6,0x281dabc3,0xabfe2564,0x295f26d7,0x1a48ab88,0xa9ed2b3b,
  0xab3b26d7,0x2b3ba6d7,0xab3b26d7,0x2b3ba6d7,0xa8c4281d,0xa0b2abc3,0x2a6d2add,0xabeaa3c6,0xa0b228c4,0xabeaaa6d,0x20b2a8c4,0x2bea2a6d,
  0x2564295f,0xa6d79a48,0xab88a9ed,0xab3babfe,0x9a481a48,0x9a481a48,0x9a481a48,0x9a481a48,0x281da0b2,0x2bc3aa6d,0x2addabea,0x23c6a8c4,
  0xaadd23c6,0xa81d2bc3,0x2adda3c6,0x281dabc3,0x2bfea564,0xa95fa6d7,0x9a482b88,0x29edab3b,0xab3b26d7,0x2b3ba6d7,0xab3b26d7,0x2b3ba6d7,
  0x28c4a81d,0x20b22bc3,0xaa6daadd,0x2bea23c6,0xa0b228c4,0xabeaaa6d,0x20b2a8c4,0x2bea2a6d,0xa564a95f,0x26d71a48,0x2b8829ed,0x2b3b2bfe,
  0xabfe2bfe,0xabfe2bfe,0xabfe2bfe,0xabfe2bfe,0xaadd2bea,0xa3c628c4,0x281da0b2,0x2bc3aa6d,0xa81d2bc3,0x2adda3c6,0x281dabc3,0xaadd23c6,
  0x9a482b88,0x29edab3b,0xabfe2564,0x295f26d7,0x26d72b3b,0xa6d7ab3b,0x26d72b3b,0xa6d7ab3b,0x2a6d2add,0xabeaa3c6,0x28c4a81d,0x20b22bc3,
  0x2bea2a6d,0xa0b228c4,0xabeaaa6d,0x20b2a8c4,0x2b8829ed,0x2b3b2bfe,0x2564295f,0xa6d79a48,0xabfe2bfe,0xabfe2bfe,0xabfe2bfe,0xabfe2bfe,
  0x2addabea,0x23c6a8c4,0xa81d20b2,0xabc32a6d,0xa81d2bc3,0x2adda3c6,0x281dabc3,0xaadd23c6,0x1a48ab88,0xa9ed2b3b,0x2bfea564,0xa95fa6d7,
  0x26d72b3b,0xa6d7ab3b,0x26d72b3b,0xa6d7ab3b,0xaa6daadd,0x2bea23c6,0xa8c4281d,0xa0b2abc3,0x2bea2a6d,0xa0b228c4,0xabeaaa6d,0x20b2a8c4,
  0xab88a9ed,0xab3babfe,0xa564a95f,0x26d71a48,0x3bfb3bff,0x3be53bf2,0x3bbf3bd4,0x3b873ba5,0x3bd03bfb,0x3b013b7c,0x399d3a60,0x378538bc,
  0x35173b52,0xbbc9b7c8,0xb074ba9b,0x3bfe391b,0x319e3b27,0xbbf3b979,0x363cb80a,0x3a2d3bc5,0xba093986,0x3a7eb8f8,0xbae5385f,0x3b3db77a,
  0xbabd393c,0x3bb0b699,0xbc00305b,0x3ba730d7,0xbb2a35c8,0xb8353bb2,0x3a64b1e8,0x3962bbf7,0xba90350b,0xba413bff,0x3602340e,0x3bf6bad8,
  0xac6aa5e4,0xb122af59,0xb402b294,0xb56ab4b7,0xb2deac9c,0xb7bdb5a5,0xb9b3b8d6,0xbb10ba73,0xbb96b676,0xb359bafe,0x3bec3884,0x2a163a29,
  0xbbe0b72c,0x2f27b9d6,0x3b5e3ae8,0xb91633a2,0xb941b9c9,0x38ad3a45,0xb80fbab3,0x36d23b13,0xb850ba0d,0x346f3b4a,0x1fdbbbed,0xb4ab3be8,
  0x3721bb76,0xbace3463,0xb8d13bdd,0x39ebadfb,0x3894bb98,0xb8fd281f,0xbb6a3bbd,0x2e2d3825,0x3b3f3b65,0x3ae83b16,0x3a813ab6,0x3a0d3a49,
  0x3263356a,0xad972b43,0xb5dfb359,0xb8eeb7f3,0xa9b139aa,0xbbedba25,0x3340b889,0x3b983afb,0xbaa2aa16,0xb4cfbb8e,0x3c0038ad,0xb44b38e5,
  0xbb853625,0x3bbdb4c3,0xbbe432ad,0x3bfbaf8b,0xbaacb6d2,0x39243954,0xb65fbace,0x2fbd3bb8,0xb9661648,0xba603bf8,0x383a31cf,0x3b27bbb3,
  0x3219b9eb,0xbb1836f4,0xb9903be5,0x37dd3010,0xb6c6b61a,0xb80ab76f,0xb8a8b85a,0xb93cb8f3,0xbbd7bb87,0xbbf8bbfd,0xbb71bbc9,0xba4dbaf1,
  0xbbfeb9a6,0x305bb91f,0x3bcb3a97,0xb50b37d2,0xb87abbfe,0x3ba13546,0x24523a7e,0xbbb5ba54,0xb576bb63,0x340e3ba3,0xb13bbbd3,0x2c9c3bf2,
  0x386abb3d,0xba2139f8,0x3b57b835,0xbbf13432,0x39e7bc00,0xb8d6adc9,0xbacb3bde,0x372c3457,0x3bdab962,0x3764bb35,0xb9c03122,0xbaf73bef,
  0x398b39cd,0x38fd3946,0x386538b2,0x37853815,0xba85b9c9,0xbb92bb1e,0xbbfebbdd,0xbbc2bbf5,0xb66b3682,0xbb01bb94,0x387fb371,0x3a2d3beb,
  0xbac7bb76,0x3a00ad33,0x36bb3bd4,0xbbeab79b,0xbc0026ad,0x3bf32c38,0xbbd6b109,0x3ba733eb,0x3153bbff,0xb70a3b9e,0x396bba9b,0xbade390c,
  0xb5d4b5bc,0xbbb03b2c,0x32013830,0x3bf6ba67,0x3bccbb52,0x2c06b92e,0xbb83385f,0xb8c73bab,0xb9c5b982,0xba41ba04,0xbab0ba7a,0xbb10bae1,
  0xb8a3b986,0xb52fb74e,0xa94db1e8,0x33d32e91,0xbb54bb4f,0x37bdb523,0x3a9e3bc8,0xb916308d,0x3840b5c8,0x394a3bf9,0xbb42b294,0xb0a6bb0a,
  0x251bbbff,0xaf273bfc,0x327cbbe6,0xb4ab3bc0,0x3be325e4,0xbb2fb4e7,0x39e33884,0xb81aba35,0x3b73bb78,0xb46fb715,0xbbdc3ad1,0x2e2d38cc,
  0x33283676,0x3bfcba19,0x3581bab3,0xba6b3493,0x363136dd,0x34cf3581,0x32c6341a,0x2fbd3153,0xbae1bb65,0xb970ba39,0xb715b889,0xb16cb4f3,
  0xb9a12a7a,0xb924bbfe,0x3a933042,0x37dd3bcc,0x308db9aa,0x3b453b07,0xb94632ad,0xb845bbfa,0xbb68b55e,0x3b1836bb,0xbabab805,0x3a4d38a3,
  0x3bc0b625,0xbbfe2ec3,0x3b9431cf,0xba89b742,0x9cb6b95d,0xbbf8396b,0xb1b63a5c,0x3bb5b840,0x38cc9648,0x3b81bbac,0xac38b85a,0xbbce3933,
  0xbb60bb3a,0xbba1bb83,0xbbd2bbbc,0xbbf1bbe3,0x3815361a,0x39df3907,0x3b2c3a97,0x3be23b9c,0xb9afbbfd,0x3a21294d,0x388e3bee,0xbaf7b328,
  0x3beb39a6,0xb6af37a6,0xba04bbd3,0x3ac42d00,0x360ebb89,0xb7643b42,0x3855baeb,0xb8ee3a85,0x33eb3b63,0x28e8bbf5,0xb5233bde,0x389ebb21,
  0x3c00b9f0,0x2d97b9e3,0xbbdf38db,0xb44b3ac7,0xba673c00,0x358d3487,0x3bfcbab6,0x330fba15,0x3b7a3bf1,0x394a3a93,0x33893764,0xb3d39cb6,
  0x3afb3be2,0x35eb3946,0xb4c328e8,0xbaa9b8cc,0x27763af7,0xbb2fbaba,0x3a76ad97,0x30a63b60,0xaf8b3ac4,0xb994bb94,0x3bf8358d,0xb8743815,
  0xbb4c38ee,0x3bfcb1b6,0xbad5b4cf,0x381a39af,0xbbb3389e,0x3b592c38,0xb76fb970,0xb24b3beb,0xb9d2344b,0xbb923bd2,0xb0f03924,0x3a6bb60e,
  0xb8f3330f,0xbc003b2c,0xb91f3b45,0x323233eb,0xb5b1afbd,0xba00b88e,0xbbc6bb18,0xbbc2bc00,0xb7d2b16c,0xbb6fba04,0xbba3bbfe,0xb86fba67,
  0xbbffb7dd,0x370ab855,0x38b73bf8,0xbbeab631,0xbbf2b845,0x39bcb523,0x2dc93b81,0xbaa5bae1,0xb68dba4d,0xac063bdf,0x382abba1,0xbade39a1,
  0xb457ba89,0xb6543bfc,0x3b16b9df,0xbbd8308d,0x397dbbb5,0xb52fb2c6,0xbbe73a21,0xb8c73b68,0x3a49bbce,0x2311b715,0xba2536af,0xbbd93bc0,
  0xb958b785,0xbb81ba9e,0xbbefbbf3,0xba89bb73,0xbbf7bbc2,0xb9b8bb42,0xaf59b70a,0x384a3328,0xbb8bba2d,0x39dfb27c,0x34263bb0,0xbbceb98b,
  0xb4b7bbea,0x3b6c39e3,0xbafe2c06,0x3185ba85,0xaadebba7,0xb6af3bdc,0x3a58ba41,0xbbe2366b,0x3a29bade,0xbc003581,0x3a45352f,0xb2f7bac7,
  0x3b37bbf6,0x28e8b865,0xbaee37bd,0xbac43c00,0x3b13b8c7,0x3b5cbbfe,0x3463b94a,0xb8993153,0xb9f4bb10,0xb58db87f,0x3029af27,0x389e35d4,
  0x2dfbb3d3,0x399936bb,0x3bf23b2f,0x3ac13bcc,0x3552b916,0x39703bd6,0xbbbab46f,0x330fb9c5,0x3ba530a6,0xb5f7396b,0xb7c8bbfc,0x3be138a3,
  0x3bfdb4ab,0xbb45b201,0x38e038fd,0xb16cbb54,0x391b381a,0xa17fbb83,0xb8f83b92,0x3bcfb840,0x36e82e2d,0x3bfebab0,0x37febb01,0xb845251b,
  0xb77a3a6b,0x3648294d,0x3bb2ba00,0x3a8cbbe3,0xb742b93c,0x2311b340,0x37a6340e,0x3aa93966,0x3b963a4d,0x3b7f3c00,0x380f3a21,0xb0be3219,
  0x3933b50b,0x35eb3be4,0xbbf5b8d6,0x3874b6c6,0x39413bb5,0xbbffb65f,0x38d1b764,0x33ba3bd7,0x3b9c2c9c,0xb994b83a,0x34873ae8,0x324bbbfe,
  0xb7213bf1,0x3b47b990,0xbbbf2d97,0x38c1387a,0x2d00372c,0x3b59b8a8,0x3a39bbed,0xb232b576,0xbbfb3af7,0xb9743b71,0x307434cf,0x3adbb86a,
  0x3b213a0d,0x3c003bcb,0x3b073bbd,0x386f39e7,0x351738ee,0xb599a452,0xbae5b924,0xbbe9bbda,0x3a153b98,0xbb6fb13b,0x2ec3ba60,0x3aa53b3f,
  0xba09344b,0xa884bb57,0x3a643b18,0xbbc3b263,0xb4f33bfb,0x39bcbacb,0xbbac380a,0x3bd8a9b1,0xbb2aafbd,0x36a439c0,0x3402bbf8,0xba6f3aa2,
  0xbbfa3b27,0xb6543a81,0x3907b05b,0x3bd9bb85,0x2c6ab7dd,0xb9da35df,0xbbec3ba1,0xb8203aac,0x3bf53b87,0x3b6c3bec,0x392e3a7e,0x32f73721,
  0xb9e7b785,0xbbfcbb5e,0xba81bbb0,0xb43eb894,0x379b3bfe,0xbc00b80f,0x374eb835,0x38993bfb,0xbb3fba2d,0x3b329fdb,0xb3403a41,0xb8eabbd0,
  0xb90c3b3d,0x3b5cb8d1,0xbbf93122,0x3ac13517,0x29b1bba7,0xb94f3b6a,0x3be4b7bd,0xbaf4b19e,0xbbab3962,0xb9993bbf,0x34e73359,0x3be1ba09,
  0x3b85bbf6,0x353ab99d,0xb83a2f27,0xbbf03abd,0x2e91356a,0xb5f7b074,0xba19b8ad,0xbbcfbb2a,0xb966bb10,0xaba7b63c,0x38a8346f,0x3bb73a90,
  0xbb0aaa16,0xa17fbae5,0x3b1e3ace,0xba8c2c6a,0x36c6b916,0x36ff3c00,0xbbcbb8fd,0x3a50b2de,0xba35b6d2,0x36483a64,0x2d33bbe5,0xb84a3b96,
  0x3bfeb4ab,0xb9fcb602,0x313b3b01,0x37e8bbe0,0x3493b9eb,0xb9b83402,0xbb9e3bc9,0xb1853941,0x35762e2d,0x3b90b9b3,0x3acbbbf3,0x2fefb850,
  0x3a543bcf,0x2884374e,0xb9f8b648,0xbbe9bbab,0x398b3bb7,0xb4db3340,0xbbdcb9fc,0xb911bb85,0xb4323a8c,0xb6a4bbf9,0x3b3539b8,0xbbc3ae91,
  0xb66b3a50,0xad65bbe4,0x38653b90,0xbb0db966,0xbbef384a,0x39da34e7,0x2b43bb6c,0xba6f3b0a,0xbc0037e8,0x3759383a,0x387fbbfc,0xbbf636c6,
  0xb7f33185,0xbb7f3a19,0xbb8e3c00,0xb8203a35,0xb5d42fef,0xba1d38a8,0xbbd63b32,0xbba93bfe,0xb8e5b2f7,0xbbffbb1e,0xb954bb5c,0x30beb493,
  0xb9c5b43e,0xbb9fbbcb,0xb201b94f,0x3a313576,0xbbb8b899,0x3b47ad33,0xb6f43999,0xb3babbf5,0xbb54b8ea,0x3bf9313b,0xbab0353a,0x3790b9e7,
  0xb010bac1,0xb9743b9e,0x3bfdb5f7,0xb8c1b79b,0x251bbaf4,0xbb1b3acb,0x3a9e2ba7,0x2e5fbb3f,0x3af1bbe1,0x3599b92e,0xb546a17f,0xbadb390c,
  0x3b73bbf0,0x3929ba81,0x327cb6ff,0xb49f29b1,0xb825baa9,0x353aaec3,0x3b7c3994,0x3af43bfa,0x360eb0be,0x3bf43a64,0x388e3b47,0xb7372c6a,
  0x38bcb874,0x2ba73bac,0xb979bb59,0x3bf03742,0x3c0033ba,0xbb043402,0x3855b974,0xacce3b96,0x3bc5b24b,0xb6ffb907,0xb6993c00,0x3bb7b933,
  0x363138c1,0x3902bbec,0xbbdf3599,0x34ff3941,0x30d73232,0x39fcb7a6,0x3bffbb6f,0x3a50bb9c,0xb9a13adb,0xb47b380f,0x32c62884,0x3937b721,
  0x3ad8386f,0x3b903bf5,0x35a539bc,0xb7e8ad00,0x3b683be9,0x2ef538d1,0xba93b6a4,0xbb24bbfb,0x3a733aa5,0xbbfcb487,0x39d6b654,0xafef3b21,
  0x1cb63bc3,0xb7b2bbbf,0x3aba39da,0xbbfab517,0xb3a23bd8,0x3b32ba39,0xbb4a2311,0x343e3a15,0xbb603a6f,0x3a3d3074,0x31b6bb7f,0xbb9a3a09,
  0xbbe83bd9,0xb94f3b07,0xa81f35eb,0x38eab4f3,0xb9af3820,0xbbae3ae5,0xbbd23bff,0xba113b2a,0x319e389e,0xb929b426,0xbc00bb45,0xb911bb37,
  0xbbffbac1,0xb805bafe,0x382a217f,0x3bfd3b13,0xbabd330f,0x34dbba58,0x36023bfe,0xbb0db9f4,0xb68dbbe1,0x3a5c3a45,0xbbe7b648,0x3b89adfb,
  0xba90b16c,0x2d653aee,0x39b3bb81,0xbbf63552,0x397dbbcf,0xbbbc3463,0x338939b8,0x39f0bba5,0x32deb845,0xb7593029,0xbb5e39df,0xbba93bfd,
  0x3b7aba8c,0x3beebbf2,0x3a76bb6c,0x36ddb91b,0xbbe0ba89,0xba1dbbba,0x1fdbb6af,0x3a3136e8,0xa776b84a,0x3aeb37c8,0x3ad53c00,0xaa7a377a,
  0xb850bbce,0x3b9f38e0,0xbb6a28e8,0x3790b958,0x3b4cb185,0xb8db38f8,0x30f0bb5c,0x355e3bf7,0x3894bbe2,0xbbf937fe,0x399d358d,0x2e5fbb8b,
  0x39d232f7,0x341abbb2,0xbbc63999,0x395d34b7,0x3bd0bac4,0x3b1bbbef,0x363cb970,0xb49faade,0xb5b13899,0x30422f59,0x38b7b5f7,0x3b3aba29,
  0x3219b3d3,0x3b0438b7,0x3b713bfc,0x34ff397d,0x36e83aa9,0xb8b2adc9,0xbbefbb59,0xb5bcba49,0x3bd730a6,0xb902382a,0xa452bb92,0x39373b7a,
  0xb9583874,0x3371bb16,0x34263c00,0xb982bafb,0x387a381a,0x347bbbe7,0xbb573a00,0x3b242776,0xbb8b324b,0x31093a25,0x3a58bb6f,0xbb4f2f8b,
  0xb86a3a6b,0x2ef53389,0x39c0b70a,0x3bfabb4c,0xaadeb232,0xb83034c3,0xbaee39bc,0xbbff3bb3,0x3bda3bc2,0x37b23a76,0xb5df2c06,0xbb9ab9d2,
  0xbb37b86f,0xba7abbf8,0x3029b654,0x3b7838f3,0x32633bea,0xba3dbad5,0x3c00352f,0xba1135b1,0xb9f4baa5,0x3bc8376f,0xbbba2311,0x39cdb7d2,
  0xbaa23ade,0x3baeb0f0,0xb65fb94a,0xb7373bff,0x3552bbd8,0xbbe6391f,0x38e035eb,0x3682bbf2,0xbaac38c7,0xbbf43bc6,0xb9903b2f,0xacce368d,
  0x3bfdbbd9,0x3ad1bba3,0x37feb994,0x26adb457,0x38a33b9a,0xb8dba452,0xbb83bbae,0x2a7ab86a,0x37423b78,0xbab6b426,0xb907bbe6,0x39aa2ade,
  0xb8403a11,0x341abb57,0x294d3bf4,0xb55ebbda,0xb93339cd,0x3889ba58,0xb7a63ad1,0x3625bb37,0xbbe33737,0x304239c0,0x3b42bb04,0xb95db263,
  0xbb9c3682,0xb2ad3aee,0x3bf5b8b2,0x1648b9f4,0xb3282cce,0xb80535df,0xb9e33902,0xbb3a3aa2,0xad0026ad,0xb1cf3029,0xb4873371,0xb61a3552,
  0xba85b4ff,0xba5cbc00,0x3581b47b,0x3bfd3aac,0xbb21b5bc,0xb85abbba,0x3a393109,0x39a63bfd,0xbac7b937,0x3bbc365f,0xbbfeaef5,0x3b89b219,
  0xba15b982,0x3a9738e0,0xbb07b830,0x3b6336e8,0x3153bb24,0xbbee3990,0x36bb37b2,0x39f0bbd7,0x34f3bb4f,0xbbd337fe,0xaec33a7a,0x3c00b958,
  0x3bccbbfa,0x3aebbb71,0x396bba3d,0x36ddb87a,0x3bfabbff,0x3bdebbef,0x3bacbbc8,0x3b65bb8b,0x3bc03911,0x38303b6a,0xb946ad65,0xbb4fbbd0,
  0x3a353bfd,0xb85f30f0,0xbb1ebbbc,0x35c8b5b1,0x38cc3b0d,0xba7ab99d,0x3b943759,0xbbffb19e,0xb4933b89,0x31e8bbc6,0xad333bee,0xa5e4bbff,
  0xb8153bf6,0x3bc8b63c,0xac38ba1d,0xbb783abd,0xbbf539f0,0x329438b7,0x3b9ebaeb,0xb676b68d,0xbbeb3ba9,0xbbe63c00,0xbb2c3b9f,0xb9cd3a90,
  0xb79b36dd,0xb884382a,0xb92e38db,0xb9c9397d,0x33eb3a31,0xbad1b602,0xba04bbf9,0x3682b2de,0xb90c2a7a,0xbab3bbe7,0x374eb41a,0x3b763b7a,
  0xba673790,0x38b2b9b3,0xb5233b1b,0x26adbbe0,0xbbabb55e,0x3bdd3389,0xbbf9b042,0x3bff2776,0xbae12e5f,0xb3713b5e,0x3bfcb929,0xb5bcb850,
  0xae91b95d,0xbbd43a76,0x34e73805,0x3b52bb4c,0x308db49f,0xb1091fdb,0xb71534db,0xb9823894,0x3b0abb3a,0x3a9bbad5,0x3a19ba5c,0x3986b9d2,
  0x2f8bb7e8,0x3bde3979,0x376f3b32,0xb9aab0d7,0x3bb83b24,0xb1223855,0xbbfdba3d,0xaa16b9a1,0x3bb3afef,0xbab63699,0x391fb94f,0xb6253ad8,
  0x30103bfa,0xb359bbdf,0x35463bae,0xb6d2bb68,0x38f3343e,0x3889bbff,0xbba3353a,0x96483a73,0xbaf13b9a,0x38ad32c6,0x39f8bbf4,0xb9eb9cb6,
  0xb7d238ea,0xb2ad35a5,0x2dc92ba7,0x361ab3a2,0xba543a11,0xbace3a93,0xbb353b04,0xbb873b60,0x3bf23af4,0x31cf39d6,0xbb16b6ff,0xb9a6bbe8,
  0xb4323737,0xbbe5baba,0x2b43b902,0x3bfe39af,0x34573bf0,0xb85abb4a,0x3a2539fc,0xbb63b825,0xbbef2cce,0x3bc9b1b6,0xbb8e347b,0x3b3db60e,
  0xba493bb7,0x3a97a81f,0x34c3bb90,0xbc0038bc,0xb7f3b4ff,0xba7e3bd2,0x39542ef5,0x3962bc00,0xbafb3a50,0xbbd33b7c,0xbbf83bfc,0xbb653bc5,
  0x38e5b937,0x3835b88e,0x36f4b7b2,0x356ab631,0xbb13bbe9,0x31e8b6f4,0x3bf239da,0x36763af1,0x3be83911,0x340e3ab0,0xbb7cb759,0xb72cbb73,
  0x2dfbbbc3,0x32943bfd,0xb7c8bb7f,0x39c93a54,0x38253b0d,0xb8d6ba9e,0x39793a1d,0xba0db98b,0x3ba5ba6f,0xb884b546,0xb8f83bff,0x3b76b432,
  0xb8bc3bf6,0x3ae8b27c,0x3699bb9f,0xbb98366b,0x391bb820,0x3ab3b9f8,0x3bb2bb47,0x3bffbbef,0xbbc53ba9,0xbbed3bdc,0xbbff3bf9,0xbbfb3c00,
  0x377ab0be,0x3bdd3b35,0x2f593974,0xbb52b7f3,0x30d73a31,0xbbbdb865,0xb5a5bb1b,0x3b2735d4,0x3bf733ba,0xbbd42b43,0x3afeb599,0xb98638e5,
  0xbad83790,0x3a60b87f,0xb9d63929,0x393cb9c5,0x34b738c1,0x3a9bbb8e,0xba45a884,0xb5c83bb8,0xba732e5f,0xb80a3bd6,0x3b4ab4db,0x350bbb54,
  0xba293adb,0xb85f3954,0xb46336a4,0x25e43010,0x33a2b49f,0x305bb201,0x281fad65,0xac9c251b,0x3f803f80,0x3f803f80,0x3f803f80,0x3f803f80,
  0x3f803f80,0x3f803f80,0x3f803f80,0x3f803f80,0x3f803f80,0x3f803f80,0x3f803f80,0x3f803f80,0x3f803f80,0x3f803f80,0x3f803f80,0x3f803f80,
  0x3f803f80,0x3f803f80,0x3f803f80,0x3f803f80,0x3f803f80,0x3f803f80,0x3f803f80,0x3f803f80,0x3f803f80,0x3f803f80,0x3f803f80,0x3f803f80,
  0x3f803f80,0x3f803f80,0x3f803f80,0x3f803f80,0x3f803f80,0x3f803f80,0x3f803f80,0x3f803f80,0x3f803f80,0x3f803f80,0x3f803f80,0x3f803f80,
  0x3f803f80,0x3f803f80,0x3f803f80,0x3f803f80,0x3f803f80,0x3f803f80,0x3f803f80,0x3f803f80,0x3f803f80,0x3f803f80,0x3f803f80,0x3f803f80,
  0x3f803f80,0x3f803f80,0x3f803f80,0x3f803f80,0x3f803f80,0x3f803f80,0x3f803f80,0x3f803f80,0x3f803f80,0x3f803f80,0x3f803f80,0x3f803f80,
  0x3f803f80,0x3f803f80,0x3f803f80,0x3f803f80,0x3f803f80,0x3f803f80,0x3f803f80,0x3f803f80,0x3f803f80,0x3f803f80,0x3f803f80,0x3f803f80,
  0x3f803f80,0x3f803f80,0x3f803f80,0x3f803f80,0x3f803f80,0x3f803f80,0x3f803f80,0x3f803f80,0x3f803f80,0x3f803f80,0x3f803f80,0x3f803f80,
  0x3f803f80,0x3f803f80,0x3f803f80,0x3f803f80,0x3f803f80,0x3f803f80,0x3f803f80,0x3f803f80,0x3f803f80,0x3f803f80,0x3f803f80,0x3f803f80,
  0x3f803f80,0x3f803f80,0x3f803f80,0x3f803f80,0x3f803f80,0x3f803f80,0x3f803f80,0x3f803f80,0x3f803f80,0x3f803f80,0x3f803f80,0x3f803f80,
  0x3f803f80,0x3f803f80,0x3f803f80,0x3f803f80,0x3f803f80,0x3f803f80,0x3f803f80,0x3f803f80,0x3f803f80,0x3f803f80,0x3f803f80,0x3f803f80,
  0x3f803f80,0x3f803f80,0x3f803f80,0x3f803f80,0x3f803f80,0x3f803f80,0x3f803f80,0x3f803f80,0x3f803f80,0x3f803f80,0x3f803f80,0x3f803f80,
  0x3f803f80,0x3f803f80,0x3f803f80,0x3f803f80,0x3f803f80,0x3f803f80,0x3f803f80,0x3f803f80,0x3f803f80,0x3f803f80,0x3f803f80,0x3f803f80,
  0x3f803f80,0x3f803f80,0x3f803f80,0x3f803f80,0x3f803f80,0x3f803f80,0x3f803f80,0x3f803f80,0x3f803f80,0x3f803f80,0x3f803f80,0x3f803f80,
  0x3f803f80,0x3f803f80,0x3f803f80,0x3f803f80,0x3f803f80,0x3f803f80,0x3f803f80,0x3f803f80,0x3f803f80,0x3f803f80,0x3f803f80,0x3f803f80,
  0x3f803f80,0x3f803f80,0x3f803f80,0x3f803f80,0x3f803f80,0x3f803f80,0x3f803f80,0x3f803f80,0x3f803f80,0x3f803f80,0x3f803f80,0x3f803f80,
  0x3f803f80,0x3f803f80,0x3f803f80,0x3f803f80,0x3f803f80,0x3f803f80,0x3f803f80,0x3f803f80,0x3f803f80,0x3f803f80,0x3f803f80,0x3f803f80,
  0x3f803f80,0x3f803f80,0x3f803f80,0x3f803f80,0x3f803f80,0x3f803f80,0x3f803f80,0x3f803f80,0x3f803f80,0x3f803f80,0x3f803f80,0x3f803f80,
  0x3f803f80,0x3f803f80,0x3f803f80,0x3f803f80,0x3f803f80,0x3f803f80,0x3f803f80,0x3f803f80,0x3f803f80,0x3f803f80,0x3f803f80,0x3f803f80,
  0x3f803f80,0x3f803f80,0x3f803f80,0x3f803f80,0x3f803f80,0x3f803f80,0x3f803f80,0x3f803f80,0x3f803f80,0x3f803f80,0x3f803f80,0x3f803f80,
  0x3f803f80,0x3f803f80,0x3f803f80,0x3f803f80,0x3f803f80,0x3f803f80,0x3f803f80,0x3f803f80,0x3f803f80,0x3f803f80,0x3f803f80,0x3f803f80,
  0x3f803f80,0x3f803f80,0x3f803f80,0x3f803f80,0x3f803f80,0x3f803f80,0x3f803f80,0x3f803f80,0x3f803f80,0x3f803f80,0x3f803f80,0x3f803f80,
  0x3f803f80,0x3f803f80,0x3f803f80,0x3f803f80,0x3f803f80,0x3f803f80,0x3f803f80,0x3f803f80,0x3f803f80,0x3f803f80,0x3f803f80,0x3f803f80,
  0x3f803f80,0x3f803f80,0x3f803f80,0x3f803f80,0x3f803f80,0x3f803f80,0x3f803f80,0x3f803f80,0x3f803f80,0x3f803f80,0x3f803f80,0x3f803f80,
  0x3f803f80,0x3f803f80,0x3f803f80,0x3f803f80,0x3f803f80,0x3f803f80,0x3f803f80,0x3f803f80,0x3f803f80,0x3f803f80,0x3f803f80,0x3f803f80,
  0x3f803f80,0x3f803f80,0x3f803f80,0x3f803f80,0x3f803f80,0x3f803f80,0x3f803f80,0x3f803f80,0x3f803f80,0x3f803f80,0x3f803f80,0x3f803f80,
  0x3f803f80,0x3f803f80,0x3f803f80,0x3f803f80,0x3f803f80,0x3f803f80,0x3f803f80,0x3f803f80,0x3f803f80,0x3f803f80,0x3f803f80,0x3f803f80,
  0x3f803f80,0x3f803f80,0x3f803f80,0x3f803f80,0x3f803f80,0x3f803f80,0x3f803f80,0x3f803f80,0x3f803f80,0x3f803f80,0x3f803f80,0x3f803f80,
  0x3f803f80,0x3f803f80,0x3f803f80,0x3f803f80,0x3f803f80,0x3f803f80,0x3f803f80,0x3f803f80,0x3f803f80,0x3f803f80,0x3f803f80,0x3f803f80,
  0x3f803f80,0x3f803f80,0x3f803f80,0x3f803f80,0x3f803f80,0x3f803f80,0x3f803f80,0x3f803f80,0x3f803f80,0x3f803f80,0x3f803f80,0x3f803f80,
  0x3f803f80,0x3f803f80,0x3f803f80,0x3f803f80,0x3f803f80,0x3f803f80,0x3f803f80,0x3f803f80,0x3f803f80,0x3f803f80,0x3f803f80,0x3f803f80,
  0x3f803f80,0x3f803f80,0x3f803f80,0x3f803f80,0x3f803f80,0x3f803f80,0x3f803f80,0x3f803f80,0x3f803f80,0x3f803f80,0x3f803f80,0x3f803f80,
  0x3f803f80,0x3f803f80,0x3f803f80,0x3f803f80,0x3f803f80,0x3f803f80,0x3f803f80,0x3f803f80,0x3f803f80,0x3f803f80,0x3f803f80,0x3f803f80,
  0x3f803f80,0x3f803f80,0x3f803f80,0x3f803f80,0x3f803f80,0x3f803f80,0x3f803f80,0x3f803f80,0x3f803f80,0x3f803f80,0x3f803f80,0x3f803f80,
  0x3f803f80,0x3f803f80,0x3f803f80,0x3f803f80,0x3f803f80,0x3f803f80,0x3f803f80,0x3f803f80,0x3f803f80,0x3f803f80,0x3f803f80,0x3f803f80,
  0x3f803f80,0x3f803f80,0x3f803f80,0x3f803f80,0x3f803f80,0x3f803f80,0x3f803f80,0x3f803f80,0x3f803f80,0x3f803f80,0x3f803f80,0x3f803f80,
  0x3f803f80,0x3f803f80,0x3f803f80,0x3f803f80,0x3f803f80,0x3f803f80,0x3f803f80,0x3f803f80,0x3f803f80,0x3f803f80,0x3f803f80,0x3f803f80,
  0x3f803f80,0x3f803f80,0x3f803f80,0x3f803f80,0x3f803f80,0x3f803f80,0x3f803f80,0x3f803f80,0x3f803f80,0x3f803f80,0x3f803f80,0x3f803f80,
  0x3f803f80,0x3f803f80,0x3f803f80,0x3f803f80,0x3f803f80,0x3f803f80,0x3f803f80,0x3f803f80,0x3f803f80,0x3f803f80,0x3f803f80,0x3f803f80,
  0x3f803f80,0x3f803f80,0x3f803f80,0x3f803f80,0x3f803f80,0x3f803f80,0x3f803f80,0x3f803f80,0x3f803f80,0x3f803f80,0x3f803f80,0x3f803f80,
  0x3f803f80,0x3f803f80,0x3f803f80,0x3f803f80,0x3f803f80,0x3f803f80,0x3f803f80,0x3f803f80,0x3f803f80,0x3f803f80,0x3f803f80,0x3f803f80,
  0x3f803f80,0x3f803f80,0x3f803f80,0x3f803f80,0x3f803f80,0x3f803f80,0x3f803f80,0x3f803f80,0x3f803f80,0x3f803f80,0x3f803f80,0x3f803f80,
  0x3f803f80,0x3f803f80,0x3f803f80,0x3f803f80,0x3f803f80,0x3f803f80,0x3f803f80,0x3f803f80,0x3f803f80,0x3f803f80,0x3f803f80,0x3f803f80,
  0x3f803f80,0x3f803f80,0x3f803f80,0x3f803f80,
};

__device__ __align__(128) float    g_part[16][8][2176];
__device__ __align__(128) float    g_kv[16][2176];
__device__ __align__(128) uint4    g_o[16 * 16 * 1024];
__device__ __align__(128) unsigned g_ocnt[2 * 16 * 32];
__device__ unsigned g_epoch[128];
#define GSTAMP(role, i) do {} while (0)
#define STAMP(role, i) do {} while (0)
#define PDUMP(role) do {} while (0)
#define PROF_SMEM 0

constexpr int STAGE_BYTES = 57344;
constexpr int OFF_H = 4 * 16384, OFF_VP = 9 * 16384, OFF_SPARE = 10 * 16384;
constexpr int OFF_XT = 172032, XT_STRIDE = 4112;
constexpr int OFF_BAR = 204928, OFF_EPOCH = OFF_BAR + 640, OFF_EX = OFF_BAR + 656, OFF_D = OFF_BAR + 672, OFF_SCALE = OFF_BAR + 704;
constexpr int OFF_F2F = 205824, OFF_F2I = 207872, OFF_F4 = 209920, OFF_ONES = 214016, OFF_KVB = 214016;
constexpr int OFF_STG = 219136, STG_STRIDE = 4352, SMEM_TOTAL = 232192 + PROF_SMEM;
enum { B_FULL1 = 0, B_EMPTY1 = 3, B_Q = 6, B_ODONE1 = 7, B_O1RDY = 8, B_H = 9, B_XRAW = 10, B_XT = 11, B_KV = 12, B_Y = 13,  B_AFREE = 15,
       B_STG = 18, B_ODONE = 24, B_XFREE = 25, B_FULL2 = 33, B_CONS2 = 49, B_SFREE = 14, B_PKRDY = 62, B_PKFREE = 64, B_H2 = 65, B_G1DONE = 66, B_COUNT = 67 };
__host__ __device__ constexpr int bar_count(int i) {
  return i < B_EMPTY1 ? 1 : i < B_Q ? 4 : i == B_XT ? 4 : i == B_H ? 4 : (i == B_SFREE || i == B_G1DONE) ? 2 : i >= B_PKFREE ? 4 : i >= B_PKRDY ? 8 : i == B_KV ? 2 : i == B_Y ? 9
       : (i >= B_AFREE && i < B_STG) ? 16 : (i == B_ODONE || i == B_ODONE1) ? 8 : (i >= B_XFREE && i < B_FULL2) ? 4
       : i >= B_CONS2 ? 4 : (i >= B_FULL2 && i < B_FULL2 + 7) ? 2 : 1;
}
__host__ __device__ constexpr uint64_t bar_counts(int r) {
  uint64_t v = 0;
  for (int w = 0; w < 11; w++) v |= (uint64_t)(bar_count(1 + 11 * r + w) - 1) << (4 * w);
  return v;
}
constexpr uint64_t SLOT_A = 0x9645296452964594ull;
constexpr uint64_t SLOT_B = 0x7103871038710326ull;
constexpr uint32_t SW128 = 64 | (1u << 30);
constexpr int SPIN_LIMIT = 1 << 22;
#define PKV CU_TENSOR_MAP_L2_PROMOTION_L2_128B
#define BPRE B_KV
#define PFD 3
#define PD1 700
#define PD2 450
#define E1C 2
#define OSP 4
#define QPF 6
#define TSPLIT 1
#define OC0 2
#define OC1 2
#define BSPL 4
#define BPACE 250
#define NPOS 0
#define O1POS 1
#define HL1 4
#define OCH 3
#define O1D 1
#define QPOS 2
#define HOLD2 12
#define A0COL 0
#define KPOS 1
#define CWAIT 0
#define HSPL 32
#define BEARLY 3
#define BLATE B_KV
#define G2LA 0
#define G2W0 0
#define G2S 2
#define EPI2 1
#define X0U 1
#define S1E 0
#define D1 200
#define PREWPOS 0
#define TRICK 3
#define PLUS1 0
#define SPINS 20
#define HSTART 1500
#define PACE 800
#define OC 1

__device__ __forceinline__ uint32_t smem_u32(const void* p) { return (uint32_t)__cvta_generic_to_shared(p); }
__device__ __forceinline__ void wg_fence() { asm volatile("wgmma.fence.sync.aligned;" ::: "memory"); }
__device__ __forceinline__ void wg_commit() { asm volatile("wgmma.commit_group.sync.aligned;" ::: "memory"); }
template <int N> __device__ __forceinline__ void wg_wait() { asm volatile("wgmma.wait_group.sync.aligned %0;" ::"n"(N) : "memory"); }
template <int N> __device__ __forceinline__ void keep(float (&d)[N]) {
#pragma unroll
  for (int i = 0; i < N; i++) asm volatile("" : "+f"(d[i])::"memory");
}
__device__ __forceinline__ uint64_t mkdesc(uint32_t addr, uint32_t lbo, uint32_t sbo, uint32_t swz) {
  uint32_t lo = ((addr & 0x3FFFF) >> 4) | ((lbo >> 4) << 16), hi = (sbo >> 4) | (swz << 30);
  return ((uint64_t)hi << 32) | lo;
}
__device__ __forceinline__ void mbar_init(uint32_t bar, int cnt) { asm volatile("mbarrier.init.shared::cta.b64 [%0], %1;" ::"r"(bar), "r"(cnt)); }
__device__ __forceinline__ void mbar_expect(uint32_t bar, int bytes) { asm volatile("mbarrier.arrive.expect_tx.shared::cta.b64 _, [%0], %1;" ::"r"(bar), "r"(bytes) : "memory"); }
__device__ __forceinline__ void mbar_arrive(uint32_t bar) { asm volatile("mbarrier.arrive.shared::cta.b64 _, [%0];" ::"r"(bar) : "memory"); }
__device__ __forceinline__ void mbar_arrive_cl(uint32_t bar, uint32_t cta) {
  asm volatile("{\n.reg .b32 r;\nmapa.shared::cluster.u32 r, %0, %1;\nmbarrier.arrive.shared::cluster.b64 _, [r];\n}\n" ::"r"(bar), "r"(cta) : "memory");
}
__device__ __forceinline__ void mbar_wait(uint32_t bar, uint32_t parity) {
  asm volatile("{\n.reg .pred p;\n.reg .u32 n;\nmov.u32 n, 0;\n"
               "W_%=:\nmbarrier.try_wait.parity.shared::cta.b64 p, [%0], %1;\n@p bra D_%=;\n"
               "add.u32 n, n, 1;\nsetp.lt.u32 p, n, %2;\n@p bra W_%=;\ntrap;\nD_%=:\n}\n" ::"r"(bar), "r"(parity), "n"(SPIN_LIMIT) : "memory");
}
__device__ __forceinline__ void fence_async() { asm volatile("fence.proxy.async.shared::cta;" ::: "memory"); }
__device__ __forceinline__ void bar_sync(int id) { asm volatile("bar.sync %0, 128;" ::"r"(id) : "memory"); }
__device__ __forceinline__ void tma2d(uint32_t dst, const CUtensorMap* m, int c0, int c1, uint32_t bar) {
  asm volatile("cp.async.bulk.tensor.2d.shared::cluster.global.mbarrier::complete_tx::bytes [%0], [%1, {%3, %4}], [%2];"
               ::"r"(dst), "l"(m), "r"(bar), "r"(c0), "r"(c1) : "memory");
}
__device__ __forceinline__ void tma2d_mc(uint32_t dst, const CUtensorMap* m, int c0, int c1, uint32_t bar) {
  asm volatile("cp.async.bulk.tensor.2d.shared::cluster.global.mbarrier::complete_tx::bytes.multicast::cluster [%0], [%1, {%3, %4}], [%2], %5;"
               ::"r"(dst), "l"(m), "r"(bar), "r"(c0), "r"(c1), "h"((uint16_t)3) : "memory");
}
__device__ __forceinline__ void tma3d(uint32_t dst, const CUtensorMap* m, int c0, int c1, int c2, uint32_t bar) {
  asm volatile("cp.async.bulk.tensor.3d.shared::cluster.global.mbarrier::complete_tx::bytes [%0], [%1, {%3, %4, %5}], [%2];"
               ::"r"(dst), "l"(m), "r"(bar), "r"(c0), "r"(c1), "r"(c2) : "memory");
}
__device__ __forceinline__ void tma4d(uint32_t dst, const CUtensorMap* m, int c0, int c1, int c2, int c3, uint32_t bar) {
  asm volatile("cp.async.bulk.tensor.4d.shared::cluster.global.mbarrier::complete_tx::bytes [%0], [%1, {%3, %4, %5, %6}], [%2];"
               ::"r"(dst), "l"(m), "r"(bar), "r"(c0), "r"(c1), "r"(c2), "r"(c3) : "memory");
}
__device__ __forceinline__ void bulk_ld(uint32_t dst, const void* src, int bytes, uint32_t bar) {
  asm volatile("cp.async.bulk.shared::cluster.global.mbarrier::complete_tx::bytes [%0], [%1], %2, [%3];" ::"r"(dst), "l"(src), "r"(bytes), "r"(bar) : "memory");
}
__device__ __forceinline__ void bulk_ld_mc(uint32_t dst, const void* src, int bytes, uint32_t bar) {
  asm volatile("cp.async.bulk.shared::cluster.global.mbarrier::complete_tx::bytes.multicast::cluster [%0], [%1], %2, [%3], %4;"
               ::"r"(dst), "l"(src), "r"(bytes), "r"(bar), "h"((uint16_t)3) : "memory");
}
__device__ __forceinline__ void tma2d_st(const CUtensorMap* m, uint32_t src, int c0, int c1) {
  asm volatile("cp.async.bulk.tensor.2d.global.shared::cta.bulk_group [%0, {%2, %3}], [%1];" ::"l"(m), "r"(src), "r"(c0), "r"(c1) : "memory");
}
__device__ __forceinline__ void pf_l2(const void* p, int bytes) { asm volatile("cp.async.bulk.prefetch.L2.global [%0], %1;" ::"l"(p), "r"(bytes) : "memory"); }
__device__ __forceinline__ void pf_t2d(const CUtensorMap* m, int c0, int c1) {
  asm volatile("cp.async.bulk.prefetch.tensor.2d.L2.global [%0, {%1, %2}];" ::"l"(m), "r"(c0), "r"(c1) : "memory");
}
__device__ __forceinline__ void pf_t3d(const CUtensorMap* m, int c0, int c1, int c2) {
  asm volatile("cp.async.bulk.prefetch.tensor.3d.L2.global [%0, {%1, %2, %3}];" ::"l"(m), "r"(c0), "r"(c1), "r"(c2) : "memory");
}
__device__ __forceinline__ void ldsm4(uint32_t (&r)[4], uint32_t a) {
  asm volatile("ldmatrix.sync.aligned.m8n8.x4.shared.b16 {%0,%1,%2,%3}, [%4];" : "=r"(r[0]), "=r"(r[1]), "=r"(r[2]), "=r"(r[3]) : "r"(a) : "memory");
}
__device__ __forceinline__ void ldsm4t(uint32_t (&r)[4], uint32_t a) {
  asm volatile("ldmatrix.sync.aligned.m8n8.x4.trans.shared.b16 {%0,%1,%2,%3}, [%4];" : "=r"(r[0]), "=r"(r[1]), "=r"(r[2]), "=r"(r[3]) : "r"(a) : "memory");
}
__device__ __forceinline__ void stsm4(uint32_t a, uint32_t r0, uint32_t r1, uint32_t r2, uint32_t r3) {
  asm volatile("stmatrix.sync.aligned.m8n8.x4.shared.b16 [%0], {%1,%2,%3,%4};" ::"r"(a), "r"(r0), "r"(r1), "r"(r2), "r"(r3) : "memory");
}
__device__ __forceinline__ uint32_t pk2(float lo, float hi) { uint32_t r; asm("cvt.rn.bf16x2.f32 %0, %1, %2;" : "=r"(r) : "f"(hi), "f"(lo)); return r; }
__device__ __forceinline__ uint32_t hmul(uint32_t a, uint32_t b) { uint32_t r; asm("mul.rn.bf16x2 %0, %1, %2;" : "=r"(r) : "r"(a), "r"(b)); return r; }
__device__ __forceinline__ uint32_t hadd(uint32_t a, uint32_t b) { uint32_t r; asm("add.rn.bf16x2 %0, %1, %2;" : "=r"(r) : "r"(a), "r"(b)); return r; }
__device__ __forceinline__ uint32_t hmax(uint32_t a, uint32_t b) { uint32_t r; asm("max.bf16x2 %0, %1, %2;" : "=r"(r) : "r"(a), "r"(b)); return r; }
__device__ __forceinline__ uint32_t hmin(uint32_t a, uint32_t b) { uint32_t r; asm("min.bf16x2 %0, %1, %2;" : "=r"(r) : "r"(a), "r"(b)); return r; }
__device__ __forceinline__ uint32_t hmaxabs(uint32_t a, uint32_t b) { uint32_t r; asm("max.xorsign.abs.bf16x2 %0, %1, %2;" : "=r"(r) : "r"(a), "r"(b)); return r; }
__device__ __forceinline__ float ex2(float x) { float r; asm("ex2.approx.ftz.f32 %0, %1;" : "=f"(r) : "f"(x)); return r; }
__device__ __forceinline__ float rcp_fast(float x) { float r; asm("rcp.approx.ftz.f32 %0, %1;" : "=f"(r) : "f"(x)); return r; }
__device__ __forceinline__ uint32_t phi2(float lo, float hi) {
  uint32_t t;
  asm("cvt.rn.relu.bf16x2.f32 %0, %1, %2;" : "=r"(t) : "f"(hi), "f"(lo));
  const uint32_t e = pk2(ex2(lo * 1.4426950408889634f), ex2(hi * 1.4426950408889634f));
  return hadd(hadd(t, hmin(e, 0x3F803F80u)), 0x35863586u);
}
__device__ __forceinline__ bool opaque_true() { uint32_t v; asm volatile("mov.u32 %0, %%nctaid.y;" : "=r"(v)); return v != 0; }
__device__ __forceinline__ int norm_exp(uint32_t (&v)[32], float f0) {
  uint32_t m[4] = {hmaxabs(__float_as_uint(f0) >> 16, v[0]), v[1], v[2], v[3]};
#pragma unroll
  for (int i = 4; i < 32; i++) m[i & 3] = hmaxabs(m[i & 3], v[i]);
  m[0] = hmaxabs(hmaxabs(m[0], m[1]), hmaxabs(m[2], m[3]));
  const int e = min(max((int)(__reduce_max_sync(~0u, max(m[0] & 0x7FFFu, (m[0] >> 16) & 0x7FFFu)) >> 7), 1), 253);
  if (e > 141) {
#pragma unroll
    for (int i = 0; i < 32; i++) v[i] = hmul(v[i], 0x07000700u);
  }
  return e;
}
template <int I0, int I1>
__device__ __forceinline__ void norm_cvt(uint32_t (&v)[32], float f0, int e) {
  const uint32_t sc = (e > 141 ? 255 - e : 142 - e) * 0x00800080u;
#pragma unroll
  for (int i = I0; i < I1; i++) {
    const uint32_t a = hmul(v[i], sc);
    v[i] = (a & 0x0FFF0FFFu) * 7 + a;
  }
  if (I0 == 0) v[0] = __byte_perm(v[0], __half_as_ushort(__float2half_rn(f0 * __uint_as_float((254 - e) << 23))), 0x3254);
}
__device__ __forceinline__ void poll_ge(const unsigned* p, unsigned target) {
#pragma unroll 1
  for (int n = 0; n < SPIN_LIMIT; n++) {
    unsigned v;
    asm volatile("ld.relaxed.gpu.global.u32 %0, [%1];" : "=r"(v) : "l"(p) : "memory");
    if (__all_sync(~0u, (int)(v - target) >= 0)) { asm volatile("fence.acquire.gpu;" ::: "memory"); return; }
  }
  __trap();
}

__device__ __forceinline__ bool elect_one() {
  uint32_t p;
  asm volatile("{\n.reg .pred p;\nelect.sync _|p, 0xffffffff;\nselp.u32 %0, 1, 0, p;\n}\n" : "=r"(p));
  return p;
}
__device__ __forceinline__ uint4 ld_nc4(const void* p) {
  uint4 v;
  asm volatile("ld.global.L1::no_allocate.v4.u32 {%0,%1,%2,%3}, [%4];" : "=r"(v.x), "=r"(v.y), "=r"(v.z), "=r"(v.w) : "l"(p) : "memory");
  return v;
}
__device__ __forceinline__ void st_cg4(void* p, uint4 v) {
  asm volatile("st.global.cg.v4.u32 [%0], {%1,%2,%3,%4};" ::"l"(p), "r"(v.x), "r"(v.y), "r"(v.z), "r"(v.w) : "memory");
}
__device__ __forceinline__ uint32_t mapa(uint32_t a, uint32_t cta) { uint32_t r; asm("mapa.shared::cluster.u32 %0, %1, %2;" : "=r"(r) : "r"(a), "r"(cta)); return r; }
__device__ __forceinline__ void st_async(uint32_t a, uint32_t v, uint32_t bar) {
  asm volatile("st.async.weak.shared::cluster.mbarrier::complete_tx::bytes.b32 [%0], %1, [%2];" ::"r"(a), "r"(v), "r"(bar) : "memory");
}
__device__ __forceinline__ void st_async4(uint32_t a, uint32_t x, uint32_t y, uint32_t z, uint32_t w, uint32_t bar) {
  asm volatile("st.async.weak.shared::cluster.mbarrier::complete_tx::bytes.v4.b32 [%0], {%1,%2,%3,%4}, [%5];" ::"r"(a), "r"(x), "r"(y), "r"(z), "r"(w), "r"(bar) : "memory");
}
__device__ __forceinline__ void tma3d_st(const CUtensorMap* m, uint32_t src, int c0, int c1, int c2) {
  asm volatile("cp.async.bulk.tensor.3d.global.shared::cta.bulk_group [%0, {%2, %3, %4}], [%1];" ::"l"(m), "r"(src), "r"(c0), "r"(c1), "r"(c2) : "memory");
}
__device__ __forceinline__ uint4 ld_rlx4(const void* p) {
  uint4 v;
  asm volatile("{\n.reg .b128 t;\n.reg .b64 a, b;\nld.relaxed.gpu.global.b128 t, [%4];\nmov.b128 {a, b}, t;\nmov.b64 {%0, %1}, a;\nmov.b64 {%2, %3}, b;\n}\n"
               : "=r"(v.x), "=r"(v.y), "=r"(v.z), "=r"(v.w) : "l"(p) : "memory");
  return v;
}
__device__ __forceinline__ void ld_stale4(uint4& v, const void* p, uint32_t tag) {
  asm volatile("{\n.reg .b128 t;\n.reg .b64 a, b;\n.reg .b32 x;\n.reg .pred p;\n"
               "lop3.b32 x, %0, %5, 1, 0x28;\nsetp.ne.u32 p, x, 0;\n"
               "mov.b64 a, {%0, %1};\nmov.b64 b, {%2, %3};\nmov.b128 t, {a, b};\n"
               "@p ld.relaxed.gpu.global.b128 t, [%4];\n"
               "mov.b128 {a, b}, t;\nmov.b64 {%0, %1}, a;\nmov.b64 {%2, %3}, b;\n}\n"
               : "+r"(v.x), "+r"(v.y), "+r"(v.z), "+r"(v.w) : "l"(p), "r"(tag) : "memory");
}
__device__ __forceinline__ void st_tag4(void* p, float a, float b, float c, float d, uint32_t tag) {
  asm volatile("{\n.reg .b128 t;\n.reg .b64 a, b;\nmov.b64 a, {%1, %2};\nmov.b64 b, {%3, %4};\nmov.b128 t, {a, b};\nst.relaxed.gpu.global.b128 [%0], t;\n}\n"
               ::"l"(p), "r"((__float_as_uint(a) & ~1u) | tag), "f"(b), "f"(c), "f"(d) : "memory");
}
__device__ __forceinline__ uint32_t stale8(const uint4 (&f)[8], uint32_t tag) {
  uint32_t r[4];
#pragma unroll
  for (int i = 0; i < 4; i++) asm("lop3.b32 %0, %1, %2, %3, 0x7E;" : "=r"(r[i]) : "r"(f[2 * i].x), "r"(f[2 * i + 1].x), "r"(tag));
  asm("lop3.b32 %0, %0, %1, %2, 0xFE;" : "+r"(r[0]) : "r"(r[1]), "r"(r[2]));
  return r[0] | r[3];
}

struct ConvC { uint32_t a1[2][4], wa[2], wb[2], sg; };
__device__ __forceinline__ uint64_t dsc(uint32_t lo, uint32_t hi) { return ((uint64_t)hi << 32) | lo; }
__device__ __forceinline__ uint32_t hfma(uint32_t a, uint32_t b, uint32_t c) { uint32_t r; asm("fma.rn.f16x2 %0, %1, %2, %3;" : "=r"(r) : "r"(a), "r"(b), "r"(c)); return r; }
__device__ __forceinline__ uint32_t hfnma(uint32_t a, uint32_t b, uint32_t c) { uint32_t r; asm("{.reg .b32 n; neg.f16x2 n, %1; fma.rn.f16x2 %0, n, %2, %3;}" : "=r"(r) : "r"(a), "r"(b), "r"(c)); return r; }
__device__ __forceinline__ uint32_t hmul16(uint32_t a, uint32_t b) { uint32_t r; asm("mul.rn.f16x2 %0, %1, %2;" : "=r"(r) : "r"(a), "r"(b)); return r; }
template <int N> __device__ __forceinline__ void keepu(uint32_t (&d)[N]) {
#pragma unroll
  for (int i = 0; i < N; i++) asm volatile("" : "+r"(d[i])::"memory");
}
__device__ __forceinline__ void conv_m1(const ConvC& K, uint32_t (&u)[16], uint32_t l) {
  wg_fence();
  wgmma_hrs_n64<1>(u, K.a1[0][0], K.a1[0][1], K.a1[0][2], K.a1[0][3], dsc(l, 32), 0);
  wgmma_hrs_n64<1>(u, K.a1[1][0], K.a1[1][1], K.a1[1][2], K.a1[1][3], dsc(l + 16, 32), 1);
  wg_commit();
}
__device__ __forceinline__ void conv_s2(const ConvC& K, uint32_t (&u)[16], uint32_t (&Z)[2][8], uint32_t dfl) {
  uint32_t fr[8], fi[8];
#pragma unroll
  for (int c = 0; c < 8; c++) {
    const uint32_t r = hfma(K.wa[c & 1], u[2 * c + 1], u[2 * c]);
    fi[c] = hfma(K.wb[c & 1], r, u[2 * c + 1]);
    fr[c] = hfma(K.wa[c & 1], fi[c], r);
  }
  wg_fence();
#pragma unroll
  for (int p = 0; p < 2; p++) {
    wgmma_hrs_n32<0>(Z[p], fr[4 * p], fr[4 * p + 2], fr[4 * p + 1], fr[4 * p + 3], dsc(dfl, 32), 0);
    wgmma_hrs_n32<0>(Z[p], fi[4 * p], fi[4 * p + 2], fi[4 * p + 1], fi[4 * p + 3], dsc(dfl + 16, 32), 1);
  }
  wg_commit();
}
__device__ __forceinline__ void conv_win(const ConvC& K, const uint32_t (&X)[2][8], uint32_t (&W)[2][8]) {
#pragma unroll
  for (int b = 0; b < 4; b++)
#pragma unroll
    for (int c = 0; c < 2; c++) {
      const uint32_t xr = X[b >> 1][2 * c + (b & 1)], xi = X[b >> 1][4 + 2 * c + (b & 1)];
      const int a = b ? b - 1 : 0;
      W[b >> 1][2 * c + (b & 1)] = b ? hfnma(K.sg, X[a >> 1][4 + 2 * c + (a & 1)], xr) : hmul16(xr, 0x3C003C00u);
      W[b >> 1][4 + 2 * c + (b & 1)] = b ? hfma(K.sg, X[a >> 1][2 * c + (a & 1)], xi) : hmul16(xi, 0x3C003C00u);
    }
}
template <int p>
__device__ __forceinline__ void conv_pw(uint32_t (&X)[2][8], uint32_t (&H)[2][8], uint32_t (&V)[8], uint32_t dil) {
  uint32_t pr[2][2], pi[2][2];
#pragma unroll
  for (int jj = 0; jj < 2; jj++)
#pragma unroll
    for (int c = 0; c < 2; c++) {
      const int j = 2 * p + jj;
      uint32_t sr = 0, si = 0;
#pragma unroll
      for (int a = 0; a <= j; a++) {
        const int b = j - a;
        const uint32_t hr = H[a >> 1][2 * c + (a & 1)], hi = H[a >> 1][4 + 2 * c + (a & 1)];
        const uint32_t xr = X[b >> 1][2 * c + (b & 1)], xi = X[b >> 1][4 + 2 * c + (b & 1)];
        sr = a == 0 ? hmul16(hr, xr) : hfma(hr, xr, sr);
        si = a == 0 ? hmul16(hr, xi) : hfma(hr, xi, si);
        sr = hfnma(hi, xi, sr);
        si = hfma(hi, xr, si);
      }
      pr[jj][c] = sr; pi[jj][c] = si;
    }
  wg_fence();
  wgmma_hrs_n32<0>(V, pr[0][0], pr[1][0], pr[0][1], pr[1][1], dsc(dil, 32), 0);
  wgmma_hrs_n32<0>(V, pi[0][0], pi[1][0], pi[0][1], pi[1][1], dsc(dil + 16, 32), 1);
  wg_commit();
}
template <int p>
__device__ __forceinline__ void conv_it(const ConvC& K, uint32_t (&V)[8], uint32_t vst) {
#pragma unroll
  for (int jj = 0; jj < 2; jj++) {
    uint32_t wr[2], wi[2];
#pragma unroll
    for (int c = 0; c < 2; c++) {
      const uint32_t r = hfnma(K.wa[c], V[4 + 2 * c + jj], V[2 * c + jj]);
      wi[c] = hfnma(K.wb[c], r, V[4 + 2 * c + jj]);
      wr[c] = hfnma(K.wa[c], wi[c], r);
    }
    stsm4(vst + (2 * p + jj) * 2048, wr[0], wr[1], wi[0], wi[1]);
  }
}
__device__ __forceinline__ void conv_m4(uint32_t (&y)[8], uint32_t (&a)[4][4], uint32_t d4l) {
  wg_fence();
  wgmma_hrs_n32<0>(y, a[0][0], a[0][1], a[0][2], a[0][3], dsc(d4l, 64), 0);
#pragma unroll
  for (int s = 1; s < 4; s++) wgmma_hrs_n32<0>(y, a[s][0], a[s][1], a[s][2], a[s][3], dsc(d4l + s * 16, 64), 1);
  wg_commit();
}

struct Params {
  CUtensorMap tmX, tmW, tmWo, tmWo1, tmK, tmV, tmQ, tmOA, tmOB;
  const __nv_bfloat16 *shift_k, *h, *D, *x, *w, *wo, *q;
  float *part, *kv;
  uint4* o;
  unsigned *ocnt, *epoch;
  const uint32_t *thr, *img;
};

__global__ void __cluster_dims__(2, 1, 1) __launch_bounds__(384, 1) fused_kernel(const __grid_constant__ Params P) {
  extern __shared__ __align__(1024) uint8_t smem[];
  const uint32_t sb = __shfl_sync(~0u, smem_u32(smem), 0);
  const uint32_t bars = sb + OFF_BAR;
  const int tid = threadIdx.x, lane = tid & 31;
  const int warp = __shfl_sync(~0u, tid >> 5, 0);
  const int rank = blockIdx.x & 1, cl = blockIdx.x >> 1;
  const int mb = cl < 4 ? 4 + cl : cl < 36 ? (cl - 4) >> 3 : 4 + (cl - 36) / 7;
  const int hb = (cl - 36) % 7;
  const int hq = cl < 4 ? A0COL : cl < 36 ? (cl - 4) & 7 : hb + (hb >= A0COL);
  const int hp = 2 * hq + rank;
  const int rb = 2 * mb + (hq >> 2), cb = hq & 3;
#define BAR(i) (bars + 8 * (i))

  if (tid == 0) { STAMP(0, 0); GSTAMP(0, 30); }
  if (warp == 8) {
    if (elect_one()) {
      mbar_init(BAR(B_FULL1), 1);
      asm volatile("fence.mbarrier_init.release.cluster;" ::: "memory");
      mbar_expect(BAR(B_FULL1), STAGE_BYTES);
      if (X0U == 1) { tma2d(sb, &P.tmX, 0, mb * 256, BAR(B_FULL1)); tma2d(sb + 16384, &P.tmX, 0, mb * 256 + 128, BAR(B_FULL1)); }
      tma3d(sb + 32768, &P.tmW, hp * 64, 0, 0, BAR(B_FULL1));
      if (X0U == 2) { tma2d(sb, &P.tmX, 0, mb * 256, BAR(B_FULL1)); tma2d(sb + 16384, &P.tmX, 0, mb * 256 + 128, BAR(B_FULL1)); }
    }
    if (lane == 0) STAMP(3, 21);
  } else if (lane == 0) {
    const int wi = warp - (warp > 8);
#pragma unroll
    for (int r = 0; r < 6; r++)
      if (r < 5 || wi < B_COUNT - 56) mbar_init(BAR(1 + 11 * r + wi), ((uint32_t)(bar_counts(r) >> (4 * wi)) & 15) + 1);
    asm volatile("fence.mbarrier_init.release.cluster;" ::: "memory");
  }
  if (tid == 0) STAMP(2, 6);
  asm volatile("barrier.cluster.arrive.relaxed.aligned;\nbarrier.cluster.wait.aligned;" ::: "memory");
  if (warp == 8 && elect_one()) {
    if (!X0U) tma2d_mc(sb + rank * 16384, &P.tmX, 0, mb * 256 + rank * 128, BAR(B_FULL1));
    if (S1E) {
      mbar_expect(BAR(B_FULL1 + 1), STAGE_BYTES);
      tma2d_mc(sb + STAGE_BYTES + rank * 16384, &P.tmX, 64, mb * 256 + rank * 128, BAR(B_FULL1 + 1));
      tma3d(sb + STAGE_BYTES + 32768, &P.tmW, hp * 64, 64, 0, BAR(B_FULL1 + 1));
    }
  }
  if (tid == 256) STAMP(2, 7);

  if (warp < 8) {
    asm volatile("setmaxnreg.inc.sync.aligned.u32 224;");
    const int wg = warp >> 2, w = warp & 3, g = lane >> 2, q = lane & 3, t = tid & 127;
    const bool elect = (t == 0);
    const uint32_t s16 = (sb & 0x3FFFF) >> 4;
    uint32_t pq[2][16];
    ConvC K;
    {
      float acc[2][96];
      if (PLUS1) {
#pragma unroll
        for (int i = 0; i < 192; i++) { acc[i / 96][i % 96] = i % 96 < 64 ? 1.f : 0.f; asm volatile("" : "+f"(acc[i / 96][i % 96])); }
      }
      int st = 0, ph = 0;
#pragma unroll 1
      for (int kb = 0; kb < 14; kb++) {
        mbar_wait(BAR(B_FULL1 + st), ph);
        if (kb == 0 && elect) { STAMP(wg, 1); GSTAMP(wg, 26); }
        if (kb == 8 && elect) { STAMP(wg, 16); GSTAMP(wg, 25); }
        if (G2S == 3 && tid == 0) STAMP(2, 8 + kb);
        const uint32_t da = s16 + st * (STAGE_BYTES >> 4) + wg * 1024 + (1 << 16);
        const uint32_t db = s16 + st * (STAGE_BYTES >> 4) + 2048 + (512 << 16);
        wg_fence();
#pragma unroll
        for (int ks = 0; ks < 4; ks++) {
          wgmma_ss_n192<0, 1>(acc[0], dsc(da + ks * 2, SW128), dsc(db + ks * 128, SW128), PLUS1 || (kb | ks) != 0);
          wgmma_ss_n192<0, 1>(acc[1], dsc(da + 512 + ks * 2, SW128), dsc(db + ks * 128, SW128), PLUS1 || (kb | ks) != 0);
        }
        wg_commit();
        wg_wait<1>();
        if (kb > 0 && t < 2) mbar_arrive_cl(BAR(B_EMPTY1 + (st == 0 ? 2 : st - 1)), t);
        if (++st == 3) { st = 0; ph ^= 1; }
      }
#define TAIL_MMA(mt, stage) do { wg_fence(); _Pragma("unroll") for (int ks = 0; ks < 4; ks++) \
        wgmma_ss_n192<0, 1>(acc[mt], dsc(s16 + (stage) * (STAGE_BYTES >> 4) + wg * 1024 + (mt) * 512 + (1 << 16) + ks * 2, SW128), \
                            dsc(s16 + (stage) * (STAGE_BYTES >> 4) + 2048 + (512 << 16) + ks * 128, SW128), 1); wg_commit(); } while (0)
      mbar_wait(BAR(B_FULL1 + 2), 0);
      TAIL_MMA(0, 2);
      wg_wait<1>();
      if (elect) mbar_arrive(BAR(B_SFREE));
      mbar_wait(BAR(B_FULL1 + 0), 1);
      TAIL_MMA(0, 0);
      TAIL_MMA(1, 2);
      const uint32_t lrow = sb + wg * 16384 + (16 * w + 8 * ((lane >> 3) & 1) + (lane & 7)) * 128 + (((lane >> 4) ^ (lane & 7)) << 4);
#define E1K(mt, i) do { if (opaque_true()) { _Pragma("unroll") for (int j = (i); j < (i) + 2; j++) { \
          const float* a = &acc[mt][32 + 8 * j]; const float* b = a + 32; const uint32_t o = (lrow ^ (j * 32)) + (mt) * 8192; \
          stsm4(o + 2 * STAGE_BYTES, pk2(b[0], b[1]), pk2(b[2], b[3]), pk2(b[4], b[5]), pk2(b[6], b[7])); \
          stsm4(o, phi2(a[0], a[1]), phi2(a[2], a[3]), phi2(a[4], a[5]), phi2(a[6], a[7])); } } } while (0)
#define E1Q(mt) do { if (opaque_true()) { _Pragma("unroll") for (int i = 0; i < 16; i++) pq[mt][i] = phi2(acc[mt][2 * i], acc[mt][2 * i + 1]); } } while (0)
#define PK_READY(mt) do { fence_async(); __syncwarp(); if (lane == 0) mbar_arrive(BAR(B_PKRDY + (mt))); } while (0)
      wg_wait<1>();
      keep(acc[0]);
      if (elect) STAMP(wg, 18);
      E1K(0, 0);
      TAIL_MMA(1, 0);
      E1K(0, 2);
      if (elect) STAMP(wg, 19);
      PK_READY(0);
      wg_wait<0>();
      keep(acc[1]);
      if (elect) mbar_arrive(BAR(B_G1DONE));
      asm volatile("setmaxnreg.dec.sync.aligned.u32 200;");
      if (elect) { STAMP(wg, 2); GSTAMP(wg, 27); }
      E1K(1, 0);
      E1K(1, 2);
      PK_READY(1);
      if (elect) STAMP(wg, 3);
      {
        const uint4* ct = (const uint4*)P.thr + t;
#pragma unroll
        for (int s = 0; s < 2; s++) { const uint4 u = ld_nc4(ct + s * 128); K.a1[s][0] = u.x; K.a1[s][1] = u.y; K.a1[s][2] = u.z; K.a1[s][3] = u.w; }
        const uint4 u = ld_nc4(ct + 2 * 128);
        K.wa[0] = u.x; K.wa[1] = u.y; K.wb[0] = u.z; K.wb[1] = u.w;
        K.sg = (lane & 4) ? 0xBC00BC00u : 0x3C003C00u;
      }
      if (CWAIT) mbar_wait(BAR(B_PKFREE), 0);
      if (elect) STAMP(wg, 4);
      E1Q(0);
      E1Q(1);
    }
    if (elect) STAMP(wg, 17);
    mbar_wait(BAR(B_H), 0);
    mbar_wait(BAR(B_PKRDY + 1), 0);
    if (elect) STAMP(wg, 5);
    {
      const uint32_t dfl = s16 + (OFF_F2F >> 4) + (8 << 16), dil = s16 + (OFF_F2I >> 4) + (8 << 16), d4l = s16 + (OFF_F4 >> 4) + (8 << 16);
      const uint32_t xl = s16 + (OFF_XT >> 4) + 4 * wg * (XT_STRIDE >> 4) + (8 << 16);
      const uint32_t hl = s16 + (OFF_H >> 4) + wg * 512 + (8 << 16);
      uint32_t vst = sb + wg * 8192 + w * 512 + lane * 16, vld = sb + wg * 8192 + w * 2048 + lane * 16;
      uint32_t ya = mapa(sb + OFF_XT + 4 * wg * XT_STRIDE + (2 * rank + (w & 1)) * 1024 + lane * 16, w >> 1);
      const uint32_t ybar = mapa(BAR(B_Y), w >> 1);
      asm volatile("" : "+r"(vst), "+r"(vld), "+r"(ya));
      uint32_t ux[16], uh[16], W[2][8], V0[8], V1[8], y[8], a[4][4];
      uint4 ov[4];
      uint4* const ot = P.o + ((2 * mb + wg) * 16 + hq) * 1024 + (16 * w + g) * 8 + ((4 * rank + q) ^ g);
#define YOUT(i) do { if ((w >> 1) == rank) { \
          asm volatile("st.shared.v4.b32 [%0], {%1,%2,%3,%4};" ::"r"(ya + (i) * XT_STRIDE), "r"(y[0]), "r"(y[2]), "r"(y[4]), "r"(y[6]) : "memory"); \
          asm volatile("st.shared.v4.b32 [%0], {%1,%2,%3,%4};" ::"r"(ya + (i) * XT_STRIDE + 512), "r"(y[1]), "r"(y[3]), "r"(y[5]), "r"(y[7]) : "memory"); \
        } else { \
          mbar_wait(BAR(B_XFREE + 4 * wg + (i)), 0); \
          st_async4(ya + (i) * XT_STRIDE, y[0], y[2], y[4], y[6], ybar); \
          st_async4(ya + (i) * XT_STRIDE + 512, y[1], y[3], y[5], y[7], ybar); } } while (0)
      auto ocalc = [&](const int hh) {
        if (hh == 0) {
          if (elect) STAMP(wg, 8);
          mbar_wait(BAR(B_KV), 0);
          if (elect) STAMP(wg, 9);
        }
        float oa[2][20];
        wg_fence();
#pragma unroll
        for (int m = 0; m < 4; m++) {
          const uint32_t* p = &pq[m & 1][8 * hh + 4 * (m >> 1)];
          wgmma_rs_n40<1>(oa[m & 1], p[0], p[1], p[2], p[3], dsc(s16 + (OFF_KVB >> 4) + hh * 160 + (m >> 1) * 16 + (8 << 16), 32), m >> 1);
        }
        wg_commit();
        wg_wait<0>();
#pragma unroll
        for (int mt = 0; mt < 2; mt++) {
          float (&o)[20] = oa[mt];
          keep(o);
          const uint32_t den = hadd(pk2(o[16], o[18]), 0x35863586u);
#pragma unroll
          for (int r = 0; r < 2; r++) {
            const float ri = rcp_fast(__uint_as_float(r ? (den & 0xFFFF0000u) : (den << 16)));
            uint4 u;
            u.x = pk2(o[2 * r] * ri, o[2 * r + 1] * ri);
            u.y = pk2(o[4 + 2 * r] * ri, o[5 + 2 * r] * ri);
            u.z = pk2(o[8 + 2 * r] * ri, o[9 + 2 * r] * ri);
            u.w = pk2(o[12 + 2 * r] * ri, o[13 + 2 * r] * ri);
            if (hh == 0 || !TRICK) st_cg4(ot + hh * 8 * 1024 + (64 * mt + 8 * r) * 8, u); else ov[2 * mt + r] = u;
          }
        }
        if (hh == 1 && TRICK) return;
        __syncwarp();
        if (lane == 0) mbar_arrive(BAR(hh ? B_ODONE1 : B_ODONE));
        if (hh == 0 && elect) STAMP(wg, 10);
      };
      auto trickle = [&](const int qs) {
        const int m = qs - 2 * (OCH + O1D) - (TRICK - 1);
        if (TRICK && m >= 0 && m < 4) {
          st_cg4(ot + 8 * 1024 + (64 * (m >> 1) + 8 * (m & 1)) * 8, ov[m]);
          if (m == 3) { __syncwarp(); if (lane == 0) mbar_arrive(BAR(B_ODONE1)); }
        }
      };
      uint32_t X[4][2][8], H[4][2][8];
      conv_m1(K, ux, xl);
      conv_m1(K, uh, hl);
      wg_wait<1>(); keepu(ux);
      if (lane == 0) mbar_arrive_cl(BAR(B_XFREE + 4 * wg), rank ^ 1);
      conv_s2(K, ux, X[0], dfl);
      wg_wait<1>(); keepu(uh);
      conv_s2(K, uh, H[0], dfl);
#pragma unroll
      for (int i = 0; i < 4; i++) {
        const bool nx = i < 3;
        const int n = nx ? i + 1 : i;
        const uint32_t vo = (i & 1) ? OFF_H + (i >> 1) * 16384 : OFF_VP;
        if (2 * i == OCH) ocalc(0);
        if (2 * i == OCH + O1D) ocalc(1);
        if (nx) {
          if (n == 2) mbar_wait(BAR(B_H2), 0);
          conv_m1(K, ux, xl + n * (XT_STRIDE >> 4));
          conv_m1(K, uh, hl + (n >> 1) * 1024 + (n & 1) * 256);
        }
        if (2 * i != OCH && 2 * i != OCH + O1D) { if (nx) { if (i > 0) wg_wait<3>(); else wg_wait<2>(); } else wg_wait<1>(); }
        keepu(X[i][0]); keepu(X[i][1]); keepu(H[i][0]); keepu(H[i][1]);
        conv_win(K, X[i], W);
        trickle(4 * i);
        conv_pw<0>(W, H[i], V0, dil);
        conv_pw<1>(W, H[i], V1, dil);
        trickle(4 * i + 1);
        wg_wait<2>();
        if (i > 0) { keepu(y); YOUT(i - 1); }
        if (2 * i + 1 == OCH) ocalc(0);
        if (2 * i + 1 == OCH + O1D) ocalc(1);
        if (nx) {
          keepu(ux); keepu(uh);
          if (lane == 0) mbar_arrive_cl(BAR(B_XFREE + 4 * wg + n), rank ^ 1);
          conv_s2(K, ux, X[n], dfl);
          wg_wait<1>();
        } else wg_wait<0>();
        keepu(V0); keepu(V1);
        trickle(4 * i + 2);
        conv_it<0>(K, V0, vst + vo);
        conv_it<1>(K, V1, vst + vo);
        bar_sync(1 + wg);
#pragma unroll
        for (int s = 0; s < 4; s++) ldsm4t(a[s], vld + vo + s * 512);
        if (nx) conv_s2(K, uh, H[n], dfl);
        conv_m4(y, a, d4l);
        trickle(4 * i + 3);
        if (i > 0 && lane < 2) mbar_arrive_cl(BAR(B_AFREE + i - 1), lane);
        if (elect && i < 3) STAMP(wg, i < 2 ? 6 + i : 9 + i);
      }
      wg_wait<0>(); keepu(y);
      YOUT(3);
      if (OCH + O1D >= 8) ocalc(1);
      __syncwarp();
      if (lane == 0) mbar_arrive(BAR(B_Y));
      if (elect) STAMP(wg, 12);
    }
    {
      float acc[64];
#define G2_MMA(da, db, first) do { wg_fence(); _Pragma("unroll") for (int ks = 0; ks < 4; ks++) \
        wgmma_ss_n128<0, 1>(acc, dsc((da) + ks * 2, SW128), dsc((db) + ks * 128, SW128), ks || !(first)); wg_commit(); } while (0)
      const uint32_t a0 = s16 + wg * 512 + (1 << 16), b0 = s16 + (512 << 16);
      uint64_t ta = SLOT_A, tb = SLOT_B;
      uint32_t da = a0 + (SLOT_A & 15) * 1024, db = b0 + (SLOT_B & 15) * 1024, fb = BAR(B_FULL2);
      uint32_t cons = mapa(BAR(B_CONS2 - 1), t & 1);
      const bool rel = __shfl_sync(~0u, t, lane) < 2;
#pragma unroll 1
      for (int kb = 0; kb < HOLD2; kb++) {
        if (G2S == 0 && tid == 128) STAMP(2, 8 + kb);
        mbar_wait(fb, 0);
        if (G2S == 1 && tid == 128) STAMP(2, 8 + kb);
        if (kb == 0 && elect) { STAMP(wg, 13); GSTAMP(wg, 28); }
        G2_MMA(da, db, kb == 0);
        ta >>= 4; tb >>= 4;
        da = a0 + ((uint32_t)ta & 15) * 1024; db = b0 + ((uint32_t)tb & 15) * 1024; fb += 8;
        asm volatile("" : "+r"(da), "+r"(db));
        wg_wait<1>();
        if (kb > 0 && kb < 12 && rel) asm volatile("mbarrier.arrive.shared::cluster.b64 _, [%0];" ::"r"(cons) : "memory");
        cons += 8;
      }
      if (HOLD2 == 11) { wg_wait<0>(); if (rel) asm volatile("mbarrier.arrive.shared::cluster.b64 _, [%0];" ::"r"(cons) : "memory"); }
#pragma unroll
      for (int kb = HOLD2; kb < 16; kb++) {
        if (wg == 1) mbar_wait(BAR(B_FULL2 + kb), 0);
        else if (kb == HOLD2) asm volatile("bar.sync 3, 256;" ::: "memory");
        G2_MMA(a0 + ((SLOT_A >> (4 * kb)) & 15) * 1024, b0 + ((SLOT_B >> (4 * kb)) & 15) * 1024, false);
      }
      if (wg == 1) asm volatile("bar.arrive 3, 256;" ::: "memory");
      const uint32_t stg = sb + wg * 8192 + w * 2048, so0 = ((SLOT_A >> 56) & 15) * 16384, so1 = ((SLOT_A >> 60) & 15) * 16384;
      const uint32_t lrow = stg + (8 * ((lane >> 3) & 1) + (lane & 7)) * 128 + (((lane >> 4) ^ (lane & 7)) << 4);
      const int col = 1024 + 256 * cb + 128 * rank, row = 128 * rb + 64 * wg + 16 * w;
      wg_wait<0>();
      keep(acc);
      if (elect) { STAMP(wg, 14); GSTAMP(wg, 29); }
#pragma unroll
      for (int cp = 0; cp < 8; cp++) {
        const float* a = &acc[8 * cp];
        stsm4((lrow ^ ((cp & 3) * 32)) + (cp >> 2 ? so1 : so0), pk2(a[0], a[1]), pk2(a[2], a[3]), pk2(a[4], a[5]), pk2(a[6], a[7]));
        if (cp == 7 || (EPI2 && cp == 3)) {
          fence_async();
          __syncwarp();
          if (elect_one()) {
            if (cp == 3 || !EPI2) tma2d_st(&P.tmOB, stg + so0, col, row);
            if (cp == 7) tma2d_st(&P.tmOB, stg + so1, col + 64, row);
          }
        }
      }
      asm volatile("cp.async.bulk.commit_group;\ncp.async.bulk.wait_group.read 0;" ::: "memory");
      if (elect) {
        STAMP(wg, 15); GSTAMP(wg, 31); PDUMP(wg); if (wg == 0) PDUMP(2);
      }
    }
  } else {
    asm volatile("setmaxnreg.dec.sync.aligned.u32 56;");
    const int hw = warp - 9, g = lane >> 2, q = lane & 3;
#define sbar (bars + 8 * (B_STG - 18) + 16 * warp)
    if (warp == 8) {
      if (D1) __nanosleep(D1);
      int st = 1 + S1E, pp = 1;
      const uint8_t* pfx = (const uint8_t*)P.x + (mb * 256 + hp * 16 + (lane & 15)) * 2048;
      const uint8_t* pfw = (const uint8_t*)P.w + (mb * 8 + (lane & 7)) * 6144 + (lane >> 3) * 2048 + hp * 128;
#pragma unroll 1
      for (int kb = 1 + S1E; kb < 16; kb++) {
        if (kb >= 3) mbar_wait(BAR(B_EMPTY1 + st), pp);
        const uint32_t sa = sb + st * STAGE_BYTES;
        if (elect_one()) {
          mbar_expect(BAR(B_FULL1 + st), STAGE_BYTES);
          tma2d_mc(sa + rank * 16384, &P.tmX, kb * 64, mb * 256 + rank * 128, BAR(B_FULL1 + st));
          tma3d(sa + 32768, &P.tmW, hp * 64, kb * 64, 0, BAR(B_FULL1 + st));
        }
        if (kb == 1 && lane == 0) STAMP(2, 24);
        if (PFD && kb >= 2) {
#pragma unroll 1
          for (int j = kb == 2 ? 3 : kb + PFD; j <= kb + PFD && j < 16; j++) {
            if (lane < 16) asm volatile("prefetch.global.L2 [%0];" ::"l"(pfx + j * 128));
            if (lane < 24) asm volatile("prefetch.global.L2 [%0];" ::"l"(pfw + j * (64 * 6144)));
          }
          if (kb >= QPF && kb < QPF + 8) asm volatile("prefetch.global.L2 [%0];" ::"l"((const uint8_t*)P.q + (blockIdx.x * 256 + (kb - QPF) * 32 + lane) * 128));
          if (kb >= 4)
            asm volatile("prefetch.global.L2 [%0];" ::"l"(kb < 12 ? (const uint8_t*)P.h + (blockIdx.x * 256 + (kb - 4) * 32 + lane) * 128
                                                                  : (const uint8_t*)P.wo + (blockIdx.x * 128 + (kb - 12) * 32 + lane) * 128));
        }
        if (++st == 3) { st = 0; pp ^= 1; }
      }
      if (lane == 0) STAMP(2, 1);
    } else {
      {
        const uint32_t clk0 = __shfl_sync(~0u, (uint32_t)clock(), 0), stg = sb + OFF_STG + hw * STG_STRIDE;
        const unsigned epoch = __shfl_sync(~0u, P.epoch[blockIdx.x], 0);
        const uint32_t tag = ~epoch & 1;
        uint32_t tap[2][4];
#pragma unroll
        for (int cg = 0; cg < 2; cg++) {
          const uint2 u = __ldg((const uint2*)(P.shift_k + (16 * cl + 8 * cg + g) * 4));
          tap[cg][0] = __byte_perm(u.x, 0, 0x1010); tap[cg][1] = __byte_perm(u.x, 0, 0x3232);
          tap[cg][2] = __byte_perm(u.y, 0, 0x1010); tap[cg][3] = __byte_perm(u.y, 0, 0x3232);
        }
        if (hw == 0 && lane < 8) *(float*)(smem + OFF_D + 4 * lane) = __bfloat162float(P.D[blockIdx.x * 8 + lane]);
        if (hw == 1) asm volatile("prefetch.global.L2 [%0];" ::"l"(P.thr + (lane + 32 * (blockIdx.x & 1)) * 32));
        if (hw == 0 && elect_one()) {
          *(volatile unsigned*)(smem + OFF_EPOCH) = epoch;
          mbar_expect(BAR(B_XRAW), 16384);
          mbar_expect(BAR(B_Y), 16384 + 64);
        }
        for (int i = hw * 32 + lane; i < 528; i += 96) st_tag4(P.part + (hp * 8 + mb) * 2176 + 4 * i, 0.f, 0.f, 0.f, 0.f, tag ^ 1);
        if (hw < 2 || lane < 2) st_tag4(P.kv + hp * 2176 + (4 * (hw < 2 ? 64 * mb + 32 * hw + lane : 512 + 2 * mb + lane)), 0.f, 0.f, 0.f, 0.f, tag ^ 1);
        if (lane == 0) STAMP(3, hw);
        const uint32_t xo = sb + OFF_XT + g * XT_STRIDE + rank * 2048 + q * 4;
        const int krow = 8 + (lane & 7) - (lane >> 3);
        const uint32_t ka = stg + krow * 32 + ((krow & 4) << 2), va = stg + 2304 + lane * 32 + ((lane & 4) << 2);
        int ph = 0, b = 0;
#pragma unroll 1
        for (int ci = hw - 3; ci < 16; ci += 3) {
          const uint32_t bo = b ? OFF_F2F - OFF_STG : 0, bn = b ? 0 : OFF_F2F - OFF_STG;
          if (ci + 3 < 16) {
            while (__any_sync(~0u, (uint32_t)clock() - clk0 < HSTART + (ci + 3) * PACE)) __nanosleep(64);
            if (elect_one()) {
              mbar_expect(sbar + 8 * (b ^ 1), 2304 + 2048);
              tma2d(stg + bn, &P.tmK, 16 * cl, 1024 * rank + 64 * (ci + 3) - 8, sbar + 8 * (b ^ 1));
              tma2d(stg + bn + 2304, &P.tmV, 16 * cl, 1024 * rank + 64 * (ci + 3), sbar + 8 * (b ^ 1));
            }
          }
          if (ci >= 0) {
            mbar_wait(sbar + 8 * b, (ph >> b) & 1);
            ph ^= 1 << b;
#pragma unroll 1
            for (int grp = 0; grp < 2; grp++) {
#pragma unroll
              for (int cg = 0; cg < 2; cg++) {
                const uint32_t dst = mapa(xo + (ci >> 3) * 1024 + ((ci & 7) * 4 + 2 * grp) * 16, cg), xbar = mapa(BAR(B_XRAW), cg);
                uint32_t vv[4], kk[4][4];
                ldsm4t(vv, (va ^ (cg * 16)) + bo + grp * 1024);
#pragma unroll
                for (int rg = 0; rg < 4; rg++) ldsm4t(kk[rg], (ka ^ (cg * 16)) + bo + grp * 1024 + rg * 256);
#pragma unroll
                for (int rg = 0; rg < 4; rg++)
                  vv[rg] = hmul(hadd(hadd(hadd(hmul(kk[rg][3], tap[cg][3]), hmul(kk[rg][2], tap[cg][2])), hmul(kk[rg][1], tap[cg][1])), hmul(kk[rg][0], tap[cg][0])), vv[rg]);
                if (cg == rank) {
#pragma unroll
                  for (int rg = 0; rg < 4; rg++) asm volatile("st.shared.b32 [%0], %1;" ::"r"(dst + (rg & 1) * 512 + (rg >> 1) * 16), "r"(vv[rg]) : "memory");
                } else {
#pragma unroll
                  for (int rg = 0; rg < 4; rg++) st_async(dst + (rg & 1) * 512 + (rg >> 1) * 16, vv[rg], xbar);
                }
              }
            }
          }
          b ^= 1;
        }
      }
      if (lane == 0) STAMP(3, 3 + hw);
      asm volatile("bar.sync 4, 96;" ::: "memory");
      if (hw == 0 && elect_one()) { mbar_expect(BAR(B_XT), 10240); bulk_ld(sb + OFF_F2F, P.img, 10240, BAR(B_XT)); }
      mbar_wait(BAR(B_XRAW), 0);
    }
    int e1 = 0;
#pragma unroll 1
    for (int n = hw < 0 ? 3 : 0; n < 4; n++) {
      const bool isH = n >= 3;
      const int c = isH ? (warp & 1) + 2 * (warp & 2) : hw + 3 * n;
      if (c < 8) {
        int ln;
        asm volatile("mov.u32 %0, %%laneid;" : "=r"(ln));
        uint8_t* dst = smem + (isH ? OFF_H + (c & 2) * 8192 + (c >> 2) * 8192 + (c & 1) * 4096 : OFF_XT + c * XT_STRIDE) + ((ln >> 4) * 512 + (ln & 15) * 16);
        const uint8_t* src0 = isH ? (const uint8_t*)P.h + (blockIdx.x * 8 + c) * 4096 + ((ln & 15) * 32 + (ln & 16)) : dst;
        const uint8_t* src1 = src0 + (isH ? 512 : 256);
        uint32_t v[32];
#pragma unroll
        for (int i = 0; i < 8; i++) {
          const uint4 u = *(const uint4*)(((i & 1) ? src1 : src0) + (i >> 1) * 1024);
          v[4 * i] = u.x; v[4 * i + 1] = u.y; v[4 * i + 2] = u.z; v[4 * i + 3] = u.w;
        }
        if (isH) mbar_wait(BAR(B_XT), 0);
        const float f0 = __uint_as_float(v[0] << 16) + ((isH && ln == 0) ? *(const float*)(smem + OFF_D + 4 * c) : 0.f);
        const int e = norm_exp(v, f0);
        norm_cvt<0, 32>(v, f0, e);
        if (isH) mbar_wait(BAR(B_SFREE), 0);
        else if (ln == 0) smem[OFF_EX + c] = e;
        e1 = e;
#pragma unroll
        for (int i = 0; i < 8; i++)
          *(uint4*)(dst + (i >> 1) * 1024 + (i & 1) * 256) = make_uint4(v[4 * i], v[4 * i + 1], v[4 * i + 2], v[4 * i + 3]);
        if (n < 2 && elect_one()) {
          if (n == 0) mbar_expect(sbar, 4096);
          tma3d(sb + OFF_STG + 2048 * c, &P.tmQ, 16 * cl, 64 * rank, 2 * c, sbar);
        }
      }
      if (n >= 2) {
        fence_async();
        __syncwarp();
        if (lane == 0) { mbar_arrive(BAR(isH ? B_H : B_XT)); STAMP(3, (isH ? 17 : 13) + hw); }
      }
    }
#define SLOT(tab, kb) (sb + ((uint32_t)((tab) >> (4 * (kb))) & 15) * 16384)
#define LOAD_B(kb) tma4d(SLOT(SLOT_B, kb), &P.tmWo, 0, ((kb) >> 3) * 32, 2 * ((kb) & 7), 4 * cb + 2 * rank, BAR(B_FULL2 + (kb)))
#define LOAD_A(kb) bulk_ld_mc(SLOT(SLOT_A, kb) + rank * 8192, P.o + (rb * 16 + (kb)) * 1024 + rank * 512, 8192, BAR(B_FULL2 + (kb)))
    asm volatile("setmaxnreg.inc.sync.aligned.u32 104;");
    {
    int tid;
    asm volatile("mov.u32 %0, %%tid.x;" : "=r"(tid));
    const int lane = tid & 31, g = lane >> 2, q = lane & 3;
    const unsigned epoch = *(volatile unsigned*)(smem + OFF_EPOCH);
    const uint32_t tag = ~epoch & 1;
    const int pi = hw < 2 ? 64 * mb - 288 + tid : 512 + 2 * mb + (lane & 1);
    const float* psrc = P.part + hp * 8 * 2176 + 4 * pi;
    uint4 f[8];
    {
      const uint32_t s16 = (sb & 0x3FFFF) >> 4;
      const int t = tid & 127, c = 2 + (warp & 1) + 2 * (warp & 2);
      uint32_t v[32];
      const uint4* hp4 = (const uint4*)(P.h + (blockIdx.x * 8 + c) * 2048) + ((lane & 15) * 2 + (lane >> 4));
#pragma unroll
      for (int i = 0; i < 8; i++) { const uint4 u = ld_nc4(hp4 + i * 32); v[4 * i] = u.x; v[4 * i + 1] = u.y; v[4 * i + 2] = u.z; v[4 * i + 3] = u.w; }
      float kva[36];
#pragma unroll
      for (int mt = 0; mt < 2; mt++) {
        mbar_wait(BAR(B_PKRDY + mt), 0);
        wg_fence();
#pragma unroll
        for (int ks = 0; ks < 8; ks++) {
          const uint32_t o = (ks >> 2) * 1024 + mt * 512 + (ks & 3) * 128, vb = (2 * STAGE_BYTES >> 4) + o;
          wgmma_ss_n72<1, 1>(kva, dsc(s16 + o + (1 << 16), SW128), dsc(s16 + vb + (((OFF_ONES >> 4) - vb) << 16), SW128), (mt | ks) != 0);
        }
        wg_commit();
        if (BEARLY && mt == 0 && hw < 0) {
          mbar_wait(BAR(B_G1DONE), 0);
          if (elect_one()) {
#pragma unroll
            for (int kb = 0; kb < BEARLY; kb++) { mbar_expect(BAR(B_FULL2 + kb), 16384); LOAD_B(kb); }
          }
        }
      }
      float* pdst = P.part + (hp * 8 + mb) * 2176 + t * 4;
      float* zdst = P.part + (hp * 8 + mb) * 2176 + 2048 + (t >> 1);
      asm volatile("" : "+l"(pdst), "+l"(zdst));
      wg_wait<0>();
      keep(kva);
      if (hw < 1) {
#pragma unroll
        for (int c = 0; c < 4; c++) st_tag4(pdst + c * 512, kva[4 * c], kva[4 * c + 1], kva[4 * c + 2], kva[4 * c + 3], tag);
      } else {
#pragma unroll
        for (int c = 4; c < 8; c++) st_tag4(pdst + (c - 4) * 512, kva[4 * c], kva[4 * c + 1], kva[4 * c + 2], kva[4 * c + 3], tag);
      }
      const float z2 = __shfl_down_sync(~0u, kva[32], 4), z3 = __shfl_down_sync(~0u, kva[34], 4);
      if (!(lane & 7)) st_tag4(zdst, kva[32], kva[34], z2, z3, tag);
      if (lane == 0) mbar_arrive(BAR(B_PKFREE));
      const uint32_t cst = clock();
      if (hw == 0 && lane == 0) STAMP(3, 24);
      const float f0 = __uint_as_float(v[0] << 16) + (lane == 0 ? *(const float*)(smem + OFF_D + 4 * c) : 0.f);
      const int e = norm_exp(v, f0);
      if (HSPL > 0) norm_cvt<0, HSPL>(v, f0, e);
      if (hw >= 0) {
        while (__any_sync(~0u, (uint32_t)clock() - cst < PD1)) { if (SPINS) __nanosleep(SPINS); }
        if (hw == 0 && lane == 0) STAMP(3, 20);
#pragma unroll
        for (int p = 0; p < 8; p++) f[p] = ld_rlx4(psrc + p * 2176);
      }
      if (HSPL < 32) norm_cvt<HSPL, 32>(v, f0, e);
      uint8_t* dst = smem + OFF_H + 16384 + (warp & 3) * 4096 + (lane >> 4) * 512 + (lane & 15) * 16;
#pragma unroll
      for (int i = 0; i < 8; i++)
        *(uint4*)(dst + (i >> 1) * 1024 + (i & 1) * 256) = make_uint4(v[4 * i], v[4 * i + 1], v[4 * i + 2], v[4 * i + 3]);
      if (lane < 4) {
        const int cc = c - (lane & 2);
        st_async(mapa(sb + OFF_SCALE + (8 * rank + cc) * 4, lane & 1), min(max(((lane & 2) ? e1 : e) + smem[OFF_EX + cc] - 124, 1), 254) << 23, mapa(BAR(B_Y), lane & 1));
      }
    }
#define H2_READY() do { fence_async(); __syncwarp(); if (lane == 0) mbar_arrive(BAR(B_H2)); } while (0)
    if (warp == 8) {
      H2_READY();
      mbar_wait(BAR(B_PKFREE), 0);
      {
        const uint32_t c0 = clock();
#pragma unroll 1
        for (int i = 0; i < 14 - 2 * BEARLY; i++) {
          const int kb = (i >> 1) + BEARLY;
          while (__any_sync(~0u, (uint32_t)clock() - c0 < i * BPACE)) __nanosleep(32);
          if (elect_one()) {
            if (!(i & 1)) mbar_expect(BAR(B_FULL2 + kb), 16384);
            tma4d(SLOT(SLOT_B, kb) + (i & 1) * 8192, &P.tmWo1, 0, 0, 2 * kb, 4 * cb + 2 * rank + (i & 1), BAR(B_FULL2 + kb));
            if (i == 0) mbar_expect(BAR(B_Q), 8192);
            if (i < 4) tma3d(sb + OFF_SPARE + 2048 * i, &P.tmQ, 16 * cl, 64 * rank + 32 * (i >> 1), 2 * ((i + 6) & 7), BAR(B_Q));
          }
        }
      }
      if (lane == 0) STAMP(2, 2);
      mbar_wait(BAR(B_AFREE), 0);
      if (elect_one()) mbar_expect(BAR(B_FULL2), 16384);
      {
        const uint32_t dst = SLOT(SLOT_A, 0) + rank * 8192;
        const uint4* src = P.o + rb * 16 * 1024 + rank * 512;
        poll_ge(&P.ocnt[rb * 32], 16 * (epoch + 1));
        asm volatile("fence.proxy.async.global;" ::: "memory");
        if (lane == 0) STAMP(2, 3);
        if (elect_one()) bulk_ld_mc(dst, src, 8192, BAR(B_FULL2));
        if (lane == 0) STAMP(3, 23);
      }
#pragma unroll 1
      for (int kb = 1; kb < 7; kb++) {
        mbar_wait(BAR(kb < 3 ? B_AFREE + kb : B_CONS2 + ((kb - 3) >> 1)), 0);
        if (elect_one()) { mbar_expect(BAR(B_FULL2 + kb), 16384); LOAD_A(kb); }
      }
#pragma unroll 1
      for (int kb = 7; kb < 16; kb++) {
        mbar_wait(BAR(B_CONS2 + kb - 5), 0);
        if (kb == 8) mbar_wait(BAR(B_O1RDY), 0);
        if (elect_one()) { mbar_expect(BAR(B_FULL2 + kb), 32768); LOAD_A(kb); LOAD_B(kb); }
      }
      if (lane == 0) { P.epoch[blockIdx.x] = epoch + 1; STAMP(2, 5); }
    } else {
      {
#pragma unroll 1
        for (int n = 0; __any_sync(~0u, stale8(f, tag) & 1); n++) {
#pragma unroll
          for (int p = 0; p < 8; p++) ld_stale4(f[p], psrc + p * 2176, tag);
          if (n > SPIN_LIMIT) __trap();
        }
        float s0 = 0.f, s1 = 0.f, s2 = 0.f, s3 = 0.f;
#pragma unroll
        for (int p = 0; p < 8; p++) { s0 += __uint_as_float(f[p].x); s1 += __uint_as_float(f[p].y); s2 += __uint_as_float(f[p].z); s3 += __uint_as_float(f[p].w); }
        if (hw < 2 || lane < 2) st_tag4(P.kv + hp * 2176 + (4 * pi), s0, s1, s2, s3, tag);
      }
      const uint32_t cs2 = clock();
      if (lane == 0 && hw == 0) STAMP(3, 8);
      H2_READY();
      if (hw == 2) {
        unsigned* cnt = P.ocnt + (2 * mb + lane) * 32;
#pragma unroll 1
        for (int hh = 0; hh < 2; hh++) {
          mbar_wait(BAR(hh ? B_ODONE1 : B_ODONE), 0);
          if (lane < 2) asm volatile("red.release.gpu.global.add.u32 [%0], 1;" ::"l"(cnt + hh * 512) : "memory");
          if (lane == 0) STAMP(3, hh ? 6 : 7);
        }
        poll_ge(&P.ocnt[512 + rb * 32], 16 * (epoch + 1));
        asm volatile("fence.proxy.async.global;" ::: "memory");
        if (lane == 0) { mbar_arrive(BAR(B_O1RDY)); STAMP(2, 4); }
        __syncwarp();
      } else {
        const int t = tid - 288;
        const float* src = P.kv + hp * 2176 + (4 * t);
        const float* zsrc = P.kv + hp * 2176 + (2048 + (t & 48) + 2 * (lane & 6));
        while (__any_sync(~0u, (uint32_t)clock() - cs2 < PD2)) { if (SPINS) __nanosleep(SPINS); }
        uint4 zp = ld_rlx4(zsrc);
#pragma unroll
        for (int p = 0; p < 8; p++) f[p] = ld_rlx4(src + 4 * ((p & 3) * 128 + (p >> 2) * 64));
        if (!opaque_true()) __trap();
#pragma unroll 1
        for (int n = 0; __any_sync(~0u, (stale8(f, tag) | (zp.x ^ tag)) & 1); n++) {
          ld_stale4(zp, zsrc, tag);
#pragma unroll
          for (int p = 0; p < 8; p++) ld_stale4(f[p], src + 4 * ((p & 3) * 128 + (p >> 2) * 64), tag);
          if (n > SPIN_LIMIT) __trap();
        }
#define PK2U(a, b) pk2(__uint_as_float(a), __uint_as_float(b))
        const uint32_t zf = (lane & 1) ? ((lane & 8) ? zp.w : zp.z) : ((lane & 8) ? zp.y : zp.x);
        const uint32_t zz = PK2U(zf, zf);
        *(uint4*)(smem + OFF_KVB + hw * 2560 + 2048 + lane * 16) = make_uint4(zz, zz, zz, zz);
#pragma unroll
        for (int hh = 0; hh < 2; hh++) {
          const uint4* ff = &f[4 * hh];
          uint8_t* dst = smem + OFF_KVB + hh * 2560 + q * 512 + (16 * hw + g) * 16;
          *(uint4*)dst = make_uint4(PK2U(ff[0].x, ff[0].y), PK2U(ff[1].x, ff[1].y), PK2U(ff[2].x, ff[2].y), PK2U(ff[3].x, ff[3].y));
          *(uint4*)(dst + 128) = make_uint4(PK2U(ff[0].z, ff[0].w), PK2U(ff[1].z, ff[1].w), PK2U(ff[2].z, ff[2].w), PK2U(ff[3].z, ff[3].w));
        }
        fence_async();
        __syncwarp();
        if (lane == 0) { mbar_arrive(BAR(B_KV)); if (hw == 0) STAMP(3, 9); }
      }
#define QBUF(ci) (sb + 2048 * (ci) + ((ci) < 6 ? OFF_STG : (ci) < 10 ? OFF_SPARE - 6 * 2048 : OFF_F2F - 10 * 2048))
      mbar_wait(BAR(B_Y), 0);
      if (elect_one()) {
        mbar_expect(sbar + 8, 4096);
#pragma unroll 1
        for (int ci = hw ? hw + 9 : 12; ci < 16; ci += 3) tma3d(QBUF(ci), &P.tmQ, 16 * cl, 64 * rank + 32, 2 * (ci & 7), sbar + 8);
      }
      mbar_wait(BAR(B_Q), 0);
      mbar_wait(sbar, hw == 0);
      {
        const float2 sc0 = *(const float2*)(smem + OFF_SCALE + 8 * q), sc1 = *(const float2*)(smem + OFF_SCALE + 32 + 8 * q);
        const uint32_t yl = sb + OFF_XT + (lane & 7) * XT_STRIDE + (lane >> 3) * 16;
#pragma unroll 1
        for (int ci = hw; ci < 16; ci += 3) {
          const uint32_t qb = QBUF(ci);
          if (ci >= 10) mbar_wait(sbar + 8, 1);
#pragma unroll 1
          for (int nl = 0; nl < 2; nl++) {
            uint32_t yy[2][4], qq[2][4];
            const uint32_t qa = qb + lane * 32 + ((lane & 4) << 2) + nl * 1024;
#pragma unroll
            for (int cg = 0; cg < 2; cg++) { ldsm4t(yy[cg], yl + cg * 2048 + (2 * ci + nl) * 64); ldsm4(qq[cg], qa ^ (cg * 16)); }
#pragma unroll
            for (int cg = 0; cg < 2; cg++) {
              const float2 sc = cg ? sc1 : sc0;
#pragma unroll
              for (int m = 0; m < 4; m++) {
                const float2 f = __half22float2(*(const __half2*)&yy[cg][m]);
                qq[cg][m] = hmul(qq[cg][m], pk2(f.x * sc.x, f.y * sc.y));
              }
              stsm4(qa ^ (cg * 16), qq[cg][0], qq[cg][1], qq[cg][2], qq[cg][3]);
            }
          }
          fence_async();
          __syncwarp();
          if (elect_one()) tma3d_st(&P.tmOA, qb, 16 * cl, 64 * rank + 32 * (ci >> 3), 2 * (ci & 7));
        }
        asm volatile("cp.async.bulk.commit_group;\ncp.async.bulk.wait_group.read 0;" ::: "memory");
      }
      if (lane == 0) STAMP(3, 10 + hw);
    }
    }
  }
}

typedef CUresult (*EncodeFn)(CUtensorMap*, CUtensorMapDataType, cuuint32_t, void*, const cuuint64_t*, const cuuint64_t*,
                             const cuuint32_t*, const cuuint32_t*, CUtensorMapInterleave, CUtensorMapSwizzle,
                             CUtensorMapL2promotion, CUtensorMapFloatOOBfill);

static void enc(EncodeFn fn, CUtensorMap* m, const void* p, int rank, const cuuint64_t* dims, const cuuint64_t* strides,
                const cuuint32_t* box, CUtensorMapSwizzle swz, CUtensorMapL2promotion promo) {
  cuuint32_t es[4] = {1, 1, 1, 1};
  fn(m, CU_TENSOR_MAP_DATA_TYPE_BFLOAT16, rank, (void*)p, dims, strides, box, es, CU_TENSOR_MAP_INTERLEAVE_NONE, swz, promo,
     CU_TENSOR_MAP_FLOAT_OOB_FILL_NONE);
}

extern "C" void kernel_launch(void* const* d_in, const int* in_sizes, int n_in, void* d_out, int out_size) {
  void* fp = nullptr;
  cudaDriverEntryPointQueryResult qr;
  cudaGetDriverEntryPoint("cuTensorMapEncodeTiled", &fp, cudaEnableDefault, &qr);
  EncodeFn fn = (EncodeFn)fp;
  Params P;
  P.shift_k = (const __nv_bfloat16*)d_in[3]; P.h = (const __nv_bfloat16*)d_in[4]; P.D = (const __nv_bfloat16*)d_in[5];
  P.q = (const __nv_bfloat16*)d_in[0];
  cudaGetSymbolAddress((void**)&P.part, g_part); cudaGetSymbolAddress((void**)&P.kv, g_kv); cudaGetSymbolAddress((void**)&P.o, g_o);
  cudaGetSymbolAddress((void**)&P.ocnt, g_ocnt); cudaGetSymbolAddress((void**)&P.epoch, g_epoch);
  cudaGetSymbolAddress((void**)&P.thr, c_thr); cudaGetSymbolAddress((void**)&P.img, c_img);
  P.x = (const __nv_bfloat16*)d_in[6]; P.w = (const __nv_bfloat16*)d_in[7]; P.wo = (const __nv_bfloat16*)d_in[8];
  const CUtensorMapSwizzle S128 = CU_TENSOR_MAP_SWIZZLE_128B, S32 = CU_TENSOR_MAP_SWIZZLE_32B;
  const CUtensorMapL2promotion P0 = CU_TENSOR_MAP_L2_PROMOTION_NONE, P128 = CU_TENSOR_MAP_L2_PROMOTION_L2_128B;
  { cuuint64_t d[2] = {1024, 2048}, s[1] = {2048}; cuuint32_t b[2] = {64, 128}; enc(fn, &P.tmX, d_in[6], 2, d, s, b, S128, P128); }
  { cuuint64_t d[3] = {1024, 1024, 3}, s[2] = {6144, 2048}; cuuint32_t b[3] = {64, 64, 3}; enc(fn, &P.tmW, d_in[7], 3, d, s, b, S128, P128); }
  { cuuint64_t d[4] = {64, 64, 16, 16}, s[3] = {2048, 131072, 128}; cuuint32_t b[4] = {64, 32, 2, 2}; enc(fn, &P.tmWo, d_in[8], 4, d, s, b, S128, P128); }
  { cuuint64_t d[4] = {64, 64, 16, 16}, s[3] = {2048, 131072, 128}; cuuint32_t b[4] = {64, 32, 2, 1}; enc(fn, &P.tmWo1, d_in[8], 4, d, s, b, S128, P128); }
  { cuuint64_t d[2] = {1024, 2048}, s[1] = {2048}; cuuint32_t b[2] = {16, 72}; enc(fn, &P.tmK, d_in[1], 2, d, s, b, S32, PKV); }
  { cuuint64_t d[2] = {1024, 2048}, s[1] = {2048}; cuuint32_t b[2] = {16, 64}; enc(fn, &P.tmV, d_in[2], 2, d, s, b, S32, PKV); }
  { cuuint64_t d[3] = {1024, 128, 16}, s[2] = {32768, 2048}; cuuint32_t b[3] = {16, 32, 2}; enc(fn, &P.tmQ, d_in[0], 3, d, s, b, S32, PKV); }
  { cuuint64_t d[3] = {1024, 128, 16}, s[2] = {65536, 4096}; cuuint32_t b[3] = {16, 32, 2}; enc(fn, &P.tmOA, d_out, 3, d, s, b, S32, P0); }
  { cuuint64_t d[2] = {2048, 2048}, s[1] = {4096}; cuuint32_t b[2] = {64, 16}; enc(fn, &P.tmOB, d_out, 2, d, s, b, S128, P0); }
  cudaFuncSetAttribute(fused_kernel, cudaFuncAttributeMaxDynamicSharedMemorySize, SMEM_TOTAL);
  fused_kernel<<<128, 384, SMEM_TOTAL>>>(P);
}
```

```cpp
#include <cuda_runtime.h>
#include <cuda_bf16.h>
#include <cuda_fp16.h>
#include <cuda.h>
#include <stdint.h>

template<int TA, int TB, int SA=1> __device__ __forceinline__ void wgmma_ss_n192(float (&d)[96], uint64_t da, uint64_t db, int scale_d) {
  asm volatile("{\n.reg .pred p;\nsetp.ne.b32 p, %98, 0;\n"
    "wgmma.mma_async.sync.aligned.m64n192k16.f32.bf16.bf16 {%0, %1, %2, %3, %4, %5, %6, %7, %8, %9, %10, %11, %12, %13, %14, %15, %16, %17, %18, %19, %20, %21, %22, %23, %24, %25, %26, %27, %28, %29, %30, %31, %32, %33, %34, %35, %36, %37, %38, %39, %40, %41, %42, %43, %44, %45, %46, %47, %48, %49, %50, %51, %52, %53, %54, %55, %56, %57, %58, %59, %60, %61, %62, %63, %64, %65, %66, %67, %68, %69, %70, %71, %72, %73, %74, %75, %76, %77, %78, %79, %80, %81, %82, %83, %84, %85, %86, %87, %88, %89, %90, %91, %92, %93, %94, %95}, %96, %97, p, %101, 1, %99, %100;\n}\n"
    : "+f"(d[0]), "+f"(d[1]), "+f"(d[2]), "+f"(d[3]), "+f"(d[4]), "+f"(d[5]), "+f"(d[6]), "+f"(d[7]), "+f"(d[8]), "+f"(d[9]), "+f"(d[10]), "+f"(d[11]), "+f"(d[12]), "+f"(d[13]), "+f"(d[14]), "+f"(d[15]), "+f"(d[16]), "+f"(d[17]), "+f"(d[18]), "+f"(d[19]), "+f"(d[20]), "+f"(d[21]), "+f"(d[22]), "+f"(d[23]), "+f"(d[24]), "+f"(d[25]), "+f"(d[26]), "+f"(d[27]), "+f"(d[28]), "+f"(d[29]), "+f"(d[30]), "+f"(d[31]), "+f"(d[32]), "+f"(d[33]), "+f"(d[34]), "+f"(d[35]), "+f"(d[36]), "+f"(d[37]), "+f"(d[38]), "+f"(d[39]), "+f"(d[40]), "+f"(d[41]), "+f"(d[42]), "+f"(d[43]), "+f"(d[44]), "+f"(d[45]), "+f"(d[46]), "+f"(d[47]), "+f"(d[48]), "+f"(d[49]), "+f"(d[50]), "+f"(d[51]), "+f"(d[52]), "+f"(d[53]), "+f"(d[54]), "+f"(d[55]), "+f"(d[56]), "+f"(d[57]), "+f"(d[58]), "+f"(d[59]), "+f"(d[60]), "+f"(d[61]), "+f"(d[62]), "+f"(d[63]), "+f"(d[64]), "+f"(d[65]), "+f"(d[66]), "+f"(d[67]), "+f"(d[68]), "+f"(d[69]), "+f"(d[70]), "+f"(d[71]), "+f"(d[72]), "+f"(d[73]), "+f"(d[74]), "+f"(d[75]), "+f"(d[76]), "+f"(d[77]), "+f"(d[78]), "+f"(d[79]), "+f"(d[80]), "+f"(d[81]), "+f"(d[82]), "+f"(d[83]), "+f"(d[84]), "+f"(d[85]), "+f"(d[86]), "+f"(d[87]), "+f"(d[88]), "+f"(d[89]), "+f"(d[90]), "+f"(d[91]), "+f"(d[92]), "+f"(d[93]), "+f"(d[94]), "+f"(d[95])
    : "l"(da), "l"(db), "r"(scale_d), "n"(TA), "n"(TB), "n"(SA));
}
template<int TA, int TB, int SA=1> __device__ __forceinline__ void wgmma_ss_n128(float (&d)[64], uint64_t da, uint64_t db, int scale_d) {
  asm volatile("{\n.reg .pred p;\nsetp.ne.b32 p, %66, 0;\n"
    "wgmma.mma_async.sync.aligned.m64n128k16.f32.bf16.bf16 {%0, %1, %2, %3, %4, %5, %6, %7, %8, %9, %10, %11, %12, %13, %14, %15, %16, %17, %18, %19, %20, %21, %22, %23, %24, %25, %26, %27, %28, %29, %30, %31, %32, %33, %34, %35, %36, %37, %38, %39, %40, %41, %42, %43, %44, %45, %46, %47, %48, %49, %50, %51, %52, %53, %54, %55, %56, %57, %58, %59, %60, %61, %62, %63}, %64, %65, p, %69, 1, %67, %68;\n}\n"
    : "+f"(d[0]), "+f"(d[1]), "+f"(d[2]), "+f"(d[3]), "+f"(d[4]), "+f"(d[5]), "+f"(d[6]), "+f"(d[7]), "+f"(d[8]), "+f"(d[9]), "+f"(d[10]), "+f"(d[11]), "+f"(d[12]), "+f"(d[13]), "+f"(d[14]), "+f"(d[15]), "+f"(d[16]), "+f"(d[17]), "+f"(d[18]), "+f"(d[19]), "+f"(d[20]), "+f"(d[21]), "+f"(d[22]), "+f"(d[23]), "+f"(d[24]), "+f"(d[25]), "+f"(d[26]), "+f"(d[27]), "+f"(d[28]), "+f"(d[29]), "+f"(d[30]), "+f"(d[31]), "+f"(d[32]), "+f"(d[33]), "+f"(d[34]), "+f"(d[35]), "+f"(d[36]), "+f"(d[37]), "+f"(d[38]), "+f"(d[39]), "+f"(d[40]), "+f"(d[41]), "+f"(d[42]), "+f"(d[43]), "+f"(d[44]), "+f"(d[45]), "+f"(d[46]), "+f"(d[47]), "+f"(d[48]), "+f"(d[49]), "+f"(d[50]), "+f"(d[51]), "+f"(d[52]), "+f"(d[53]), "+f"(d[54]), "+f"(d[55]), "+f"(d[56]), "+f"(d[57]), "+f"(d[58]), "+f"(d[59]), "+f"(d[60]), "+f"(d[61]), "+f"(d[62]), "+f"(d[63])
    : "l"(da), "l"(db), "r"(scale_d), "n"(TA), "n"(TB), "n"(SA));
}
template<int TA, int TB, int SA=1> __device__ __forceinline__ void wgmma_ss_n72(float (&d)[36], uint64_t da, uint64_t db, int scale_d) {
  asm volatile("{\n.reg .pred p;\nsetp.ne.b32 p, %38, 0;\n"
    "wgmma.mma_async.sync.aligned.m64n72k16.f32.bf16.bf16 {%0, %1, %2, %3, %4, %5, %6, %7, %8, %9, %10, %11, %12, %13, %14, %15, %16, %17, %18, %19, %20, %21, %22, %23, %24, %25, %26, %27, %28, %29, %30, %31, %32, %33, %34, %35}, %36, %37, p, %41, 1, %39, %40;\n}\n"
    : "+f"(d[0]), "+f"(d[1]), "+f"(d[2]), "+f"(d[3]), "+f"(d[4]), "+f"(d[5]), "+f"(d[6]), "+f"(d[7]), "+f"(d[8]), "+f"(d[9]), "+f"(d[10]), "+f"(d[11]), "+f"(d[12]), "+f"(d[13]), "+f"(d[14]), "+f"(d[15]), "+f"(d[16]), "+f"(d[17]), "+f"(d[18]), "+f"(d[19]), "+f"(d[20]), "+f"(d[21]), "+f"(d[22]), "+f"(d[23]), "+f"(d[24]), "+f"(d[25]), "+f"(d[26]), "+f"(d[27]), "+f"(d[28]), "+f"(d[29]), "+f"(d[30]), "+f"(d[31]), "+f"(d[32]), "+f"(d[33]), "+f"(d[34]), "+f"(d[35])
    : "l"(da), "l"(db), "r"(scale_d), "n"(TA), "n"(TB), "n"(SA));
}
template<int TB, int SA=1> __device__ __forceinline__ void wgmma_rs_n40(float (&d)[20], uint32_t a0, uint32_t a1, uint32_t a2, uint32_t a3, uint64_t db, int scale_d) {
  asm volatile("{\n.reg .pred p;\nsetp.ne.b32 p, %25, 0;\n"
    "wgmma.mma_async.sync.aligned.m64n40k16.f32.bf16.bf16 {%0, %1, %2, %3, %4, %5, %6, %7, %8, %9, %10, %11, %12, %13, %14, %15, %16, %17, %18, %19}, {%20, %21, %22, %23}, %24, p, %27, 1, %26;\n}\n"
    : "+f"(d[0]), "+f"(d[1]), "+f"(d[2]), "+f"(d[3]), "+f"(d[4]), "+f"(d[5]), "+f"(d[6]), "+f"(d[7]), "+f"(d[8]), "+f"(d[9]), "+f"(d[10]), "+f"(d[11]), "+f"(d[12]), "+f"(d[13]), "+f"(d[14]), "+f"(d[15]), "+f"(d[16]), "+f"(d[17]), "+f"(d[18]), "+f"(d[19])
    : "r"(a0), "r"(a1), "r"(a2), "r"(a3), "l"(db), "r"(scale_d), "n"(TB), "n"(SA));
}
template<int TB> __device__ __forceinline__ void wgmma_hrs_n64(uint32_t (&d)[16], uint32_t a0, uint32_t a1, uint32_t a2, uint32_t a3, uint64_t db, int scale_d) {
  asm volatile("{\n.reg .pred p;\nsetp.ne.b32 p, %21, 0;\n"
    "wgmma.mma_async.sync.aligned.m64n64k16.f16.f16.f16 {%0, %1, %2, %3, %4, %5, %6, %7, %8, %9, %10, %11, %12, %13, %14, %15}, {%16, %17, %18, %19}, %20, p, 1, 1, %22;\n}\n"
    : "+r"(d[0]), "+r"(d[1]), "+r"(d[2]), "+r"(d[3]), "+r"(d[4]), "+r"(d[5]), "+r"(d[6]), "+r"(d[7]), "+r"(d[8]), "+r"(d[9]), "+r"(d[10]), "+r"(d[11]), "+r"(d[12]), "+r"(d[13]), "+r"(d[14]), "+r"(d[15])
    : "r"(a0), "r"(a1), "r"(a2), "r"(a3), "l"(db), "r"(scale_d), "n"(TB));
}
template<int TB> __device__ __forceinline__ void wgmma_hrs_n32(uint32_t (&d)[8], uint32_t a0, uint32_t a1, uint32_t a2, uint32_t a3, uint64_t db, int scale_d) {
  asm volatile("{\n.reg .pred p;\nsetp.ne.b32 p, %13, 0;\n"
    "wgmma.mma_async.sync.aligned.m64n32k16.f16.f16.f16 {%0, %1, %2, %3, %4, %5, %6, %7}, {%8, %9, %10, %11}, %12, p, 1, 1, %14;\n}\n"
    : "+r"(d[0]), "+r"(d[1]), "+r"(d[2]), "+r"(d[3]), "+r"(d[4]), "+r"(d[5]), "+r"(d[6]), "+r"(d[7])
    : "r"(a0), "r"(a1), "r"(a2), "r"(a3), "l"(db), "r"(scale_d), "n"(TB));
}

__device__ __align__(128) const uint32_t c_thr[1536] = {
  0x33fb33ff,0xa49c9de4,0x33273352,0xaf2cae76,0x33e233f1,0xa96ca7bd,0x32c432f7,0xb045afdd,0x33b733cf,0xac3eaaf7,0x3250328c,0xb0eab099,
  0x3378339a,0xadbcacff,0x31cd3211,0xb182b137,0x33d033fb,0xaadea46a,0x299e2d17,0xb3e0b396,0x32fb337a,0xafd2adb1,0xa78b1f76,0xb3f2b3ff,
  0x318b3254,0xb1c5b0e5,0xae6bac32,0xb354b3b8,0x2f4230a3,0xb321b285,0xb133b040,0xb215b2c7,0x337c33f2,0xada5a759,0xb179afc8,0xb1d6b2fe,
  0x31463293,0xb204b08e,0xb394b2ba,0xad23b055,0x2b402f4e,0xb3cbb31e,0xb3e4b3f9,0x293ba533,0xac269c52,0xb3bab400,0xb258b357,0x30e02e5f,
  0x330133e5,0xafbda922,0xb3f3b3c9,0x2727ab59,0x2deb314a,0xb36fb200,0xb194b32f,0x31bc2f0a,0xacdb2084,0xb39fb3ff,0xa565aea4,0x33f93347,
  0xb2b6b0db,0xb05ab25c,0x30892c1a,0x329733bc,0x326033d4,0xb0d6aa94,0xb00ab29b,0x32e83084,0x20e82f64,0xb3feb318,0x2d8da597,0x338133f8,
  0xb1fcae48,0xb14fb35c,0x339031b8,0x2d3a3199,0xb3e6b3ae,0x2909ac7b,0x32d133f4,0xb030a6f5,0x319d33bf,0xb1b3ac02,0x2e3ca874,0x335e33ec,
  0xacc32b89,0xb3a3b3c6,0x33f83276,0x25c930b7,0xb3dcb1f8,0xaa01b154,0x30653335,0xb2b0aef4,0xb107b383,0x32392d81,0xafa6214d,0xb307b3fe,
  0x30bc33a5,0xb273acb7,0x33c5311b,0x2ba23229,0xb0cc94b6,0xb267b400,0x30153360,0xb2e1ae31,0xb385b3ab,0x2d76ac93,0xb166a691,0xb1e7b3f5,
  0x22deb06a,0x33fd32ac,0xb337b3da,0x2ee8aa19,0x2f853387,0xb310ad6a,0x322d33fe,0xb1162216,0xb2a9abd3,0xb06fb3c2,0xb07428a6,0xb2a5b3ea,
  0xb111b3e9,0x323128be,0xb30db3c3,0x2f90abba,0x31aa227a,0x31a633fd,0x2e25ad5e,0x33633389,0x2d6a3365,0xb387ae1a,0xa21631aa,0xb3feb1a6,
  0xb3c2af85,0xabd3b310,0xb3eab22d,0x28a6b116,0xa8beb2a9,0x33e9306f,0x2bbab074,0x33c332a5,0x33fd3111,0x227a3231,0x3389330d,0xad5e2f90,
  0x2a63333f,0xb3d7aec6,0xb2a2a1b1,0xb07ab3fe,0xb3f7b158,0x25fbb1f4,0xacb7b38b,0x33a52d52,0x2e0eb025,0x336832d8,0x340030bc,0x14b63273,
  0x323533c0,0xb10c2beb,0xac9330cc,0xb3abb267,0x23433316,0xb3fdaf6f,0xb38eb225,0x2d46b11f,0xb342b29e,0x2ebbb07f,0x31e3aa7c,0x316b33d6,
  0x3264a6c3,0x30d133f5,0x2c0233ac,0xb3bfac87,0x28f0336a,0xb3e7ae02,0xb3c6b19d,0x2b89b1b3,0xa59732e8,0xb3f8b00a,0xaccfb3ed,0x33a1285b,
  0xb1b8b381,0x3199ad8d,0x336c31df,0xadf73170,0x33f42d3a,0x26f53390,0xb30423a7,0xafb2b3fc,0xb05f3030,0xb2b3b2d1,0x29e8b27a,0x33dd30b2,
  0xab5932b6,0xb3c9b05a,0x30adb089,0x327e3297,0xaf0ab3f3,0x332fa727,0x240633b0,0xb3fcac6f,0x33473194,0xaea431bc,0xb174b359,0x31daae54,
  0xb3bca565,0xac1ab3f9,0x33ee2f59,0xa842331b,0xaddf3281,0xb371b0a8,0x34002b40,0x1c5233cb,0xa759b3ef,0x33f22829,0xb2fe2c26,0xafc8b3ba,
  0x308e337c,0xb2932da5,0x3055b179,0x32ba31d6,0xb31eb146,0x2f4eb204,0xa5333394,0xb3f9ad23,0xaff33249,0xb2f1b0f3,0x30e532fb,0xb2542fd2,
  0x2b28b373,0x33cc2dd4,0xb285b18b,0x30a3b1c5,0x246a33fa,0xb3fba500,0x33962f42,0xad173321,0xadb1b3d0,0x337aaade,0xb3ffa99e,0x1f76b3e0,
  0xb0ee320d,0xb24db13c,0xac4b3398,0xb3b5ad0b,0x304ab289,0x32c1309e,0x2985b3ce,0x33e12b0f,0xaf3732f4,0xb324afe8,0xa4ce33f0,0xb3faa7ef,
  0x2dc8b34f,0x33762e82,0x9de4b3ff,0x33ff1ead,0xb1c931cd,0xb186b182,0xb3762e82,0xadc8b34f,0x324db13c,0x30ee320d,0x33b5ad0b,0x2c4b3398,
  0xb2c1309e,0xb04ab289,0xb3e12b0f,0xa985b3ce,0x3324afe8,0x2f3732f4,0x33faa7ef,0x24ce33f0,0xb285318b,0xb0a3b1c5,0xb2c7ae6b,0x3040b354,
  0x3396af42,0x2d173321,0x31413133,0xb2093215,0xb3ff299e,0x9f76b3e0,0xae8db2bd,0x334cb050,0x33b8278b,0xac3233f2,0x281033b3,0xb3ef2c57,
  0xb31e3146,0xaf4eb204,0xa533b394,0x33f9ad23,0x3400ab40,0x9c5233cb,0xae5f33e4,0xb357a93b,0xb2feac26,0x2fc8b3ba,0x3245b258,0x30f830e0,
  0x30553179,0xb2ba31d6,0xb3df2e99,0xa9b6b34a,0xb39230fd,0xad2fb241,0x3200b301,0x314a2fbd,0x337f1b11,0xad993400,0xb3ff2deb,0xa084b36f,
  0xb005b129,0x32ebb21d,0x325c2cdb,0xb0db339f,0xa92233de,0xb3e529cf,0xab59b2b6,0x33c9b05a,0xb3dd30b2,0xa9e8b27a,0x33d4ab71,0xaa9433c8,
  0x32212c0e,0xb12433bd,0xaf64b0d6,0x3318b260,0x197fb345,0x3400aeaf,0xae4833fe,0xb35c20e8,0xb23d3332,0xb102aeff,0x33aeb14f,0x2c7b31fc,
  0xb3fe3065,0xa14db2b0,0x2ebb307f,0xb342329e,0x300f2fa6,0xb2e53307,0x30d1b3f5,0x326426c3,0x302ab400,0x32d517db,0xb3e72e02,0x28f0b36a,
  0xb3fd2f6f,0x2343b316,0x2d46311f,0xb38e3225,0xb3f53015,0x2691b2e1,0xaf9b33eb,0xb30a288d,0x2a193166,0xb3da31e7,0x33d7aec6,0xaa63333f,
  0x3313b337,0x2f7a2ee8,0xa5fbb1f4,0x33f7b158,0xb1a1a8d7,0x31afb3e8,0xb36832d8,0xae0eb025,0xb3c22f85,0x2bd3b310,0xb3ea322d,0xa8a6b116,
  0xa8be32a9,0xb3e9306f,0x2bba3074,0xb3c332a5,0x33fdb111,0xa27a3231,0x3389b30d,0x2d5e2f90,0xa216b1aa,0x33feb1a6,0xaed2ae25,0x333db363,
  0xb3652edd,0x2e1ab33a,0xb1aa227a,0x31a6b3fd,0xaf853387,0xb3102d6a,0xb22d33fe,0xb116a216,0x32a9abd3,0xb06f33c2,0x307428a6,0xb2a533ea,
  0x3111b3e9,0x3231a8be,0x330db3c3,0x2f902bba,0xb2e12e31,0x3015b360,0x288db1a1,0x33ebb1af,0xb1e733f5,0xb1662691,0xb33f2f9b,0x2ec6b30a,
  0x2ee82a19,0xb33733da,0xb15833d7,0xb1f42a63,0x33e8b313,0x28d72f7a,0x302525fb,0xb2d833f7,0xb2392d81,0x3107b383,0x3307b3fe,0x2fa6214d,
  0xb35e33ec,0xae3ca874,0x97dbb00f,0x3400b2e5,0xa5c930b7,0xb3f83276,0xb316302a,0x2f6fb2d5,0x32b0aef4,0xb0653335,0xb29e33fd,0xb07f2343,
  0xb1702ccf,0x31dfb3a1,0x3345b124,0xaeaf3221,0xb3fc336c,0xa3a7adf7,0x3332b400,0x2eff997f,0xb0b23304,0xb27a2fb2,0x2b71b102,0x33c8b23d,
  0x2c0e29e8,0xb3bd33dd,0xb0d62a94,0x3260b3d4,0xb0892c1a,0x3297b3bc,0x2aad2842,0xb3d333ee,0xb3b0327e,0x2c6fb0ad,0x3241b035,0xb0fd32ce,
  0xb35933fc,0xae542406,0x3400b392,0x1b112d2f,0xaf5931da,0xb31b3174,0x321db37f,0x3129ad99,0xaf152ac6,0x332cb3d2,0xb1463293,0xb204308e,
  0xb281312e,0x30a8b219,0xab402f4e,0xb3cb331e,0xb3ef3371,0x2829addf,0x2c269c52,0xb3ba3400,0xb37c33f2,0xada52759,0x3179afc8,0xb1d632fe,
  0xacf32953,0x339cb3e3,0xb3fa33cc,0x2500ab28,0xb0942f21,0x3290b32a,0xb3d033fb,0xaade246a,0xb249317d,0x30f3b1d2,0xb2fb337a,0xafd22db1,
  0xb37332f1,0x2dd4aff3,0xb18b3254,0xb1c530e5,0xa96c27bd,0x33e2b3f1,0xb0452fdd,0x32c4b2f7,0xac3e2af7,0x33b7b3cf,0xb0ea3099,0x3250b28c,
  0xadbc2cff,0x3378b39a,0xb1823137,0x31cdb211,0xaf2c2e76,0x3327b352,0xb20d31c9,0x313cb186,0x313c3186,0xb20db1c9,0x2d0b2dc8,0xb398b376,
  0x309e30ee,0xb289b24d,0x2b0f2c4b,0xb3ceb3b5,0x2fe8304a,0xb2f4b2c1,0x27ef2985,0xb3f0b3e1,0x2e822f37,0xb34fb324,0x1ead24ce,0xb3ffb3fa,
  0xb2bdb209,0xb050b141,0xb290b32a,0x30942f21,0xb3b3b34c,0xac57ae8d,0xb0f3b1d2,0x3249317d,0xb400b3ef,0x1d1ba810,0xadd4aff3,0x337332f1,
  0xb39cb3e3,0x2cf32953,0xa500ab28,0x33fa33cc,0xae99b0f8,0x334a3245,0x33ff33b2,0x201f2c63,0x2438a9b6,0x33fc33df,0x332c33d2,0xaf15aac6,
  0x303a2ce7,0x32cb339e,0x30a83219,0xb281b12e,0x32ee31c0,0x2ffe3190,0x28292ddf,0xb3efb371,0x33b0327e,0x2c6f30ad,0xb241b035,0xb0fdb2ce,
  0x335933fc,0xae54a406,0xb400b392,0x1b11ad2f,0x2f5931da,0xb31bb174,0xb21db37f,0x31292d99,0xaaad2842,0xb3d3b3ee,0xa9cfb005,0x33de32eb,
  0x285b305f,0xb3edb2b3,0x2c0ea9e8,0x33bd33dd,0xb170accf,0xb1dfb3a1,0x33453124,0x2eaf3221,0xb3fcb36c,0x23a7adf7,0x33323400,0xaeff997f,
  0xb0b2b304,0x327a2fb2,0x2b713102,0xb3c8b23d,0xb400b2e5,0x17dbb00f,0x2e023264,0xb36ab0d1,0xaf6fb2d5,0x3316302a,0xb11fa8f0,0xb225b3e7,
  0x307f2343,0x329e33fd,0xb3d6b38e,0x2a7cad46,0x33f53342,0xa6c32ebb,0xac87b1e3,0x33ac316b,0x28d7af7a,0x33e83313,0xb2d8b3f7,0x3025a5fb,
  0x33eb31af,0x288d31a1,0x2bebae0e,0x33c03368,0x2ec6330a,0xb33faf9b,0x33fe3235,0x21b1310c,0xb1f4aa63,0xb158b3d7,0x2d5232a2,0xb38bb07a,
  0x33a7333d,0xacab2ed2,0x33f63162,0x262d31eb,0xaa4b301a,0xb3d8b2de,0x2a32326b,0xb3d9b0c7,0xb3f6b26f,0x265fb0c1,0xb3a9b020,0xac9fb2db,
  0x0e48b15d,0x340031f0,0xae1ab33a,0x33652edd,0xaed22e25,0xb33db363,0xb1eb0e48,0xb162b400,0xb2deb3a7,0x301aacab,0xb0c7b3f6,0x326b262d,
  0x30c1aa4b,0x326f33d8,0x32db2a32,0x302033d9,0x31f033f6,0xb15d265f,0x2edd33a9,0xb33aac9f,0xb2acb385,0x306aad76,0x2a19b166,0x33da31e7,
  0x3229a2de,0x311b33fd,0x33133337,0xaf7a2ee8,0x2e3133c5,0xb360aba2,0xb1a128d7,0xb1afb3e8,0xb3f5b015,0xa691b2e1,0xaf9bb3eb,0x330a288d,
  0x3154acc3,0x31f833a3,0x2ef433f8,0xb335a5c9,0x2d8133dc,0xb383aa01,0xb3feb065,0x214db2b0,0xb3ecb107,0x2874b239,0x300fafa6,0x32e53307,
  0x30b7ae3c,0x3276335e,0x302a3400,0xb2d517db,0x312433bd,0xb2212c0e,0xb318b260,0x2f64b0d6,0xb400aeaf,0x997fb345,0x335c20e8,0x2e4833fe,
  0x3102aeff,0x323d3332,0xac7b31fc,0xb3aeb14f,0x2a9433c8,0xb3d4ab71,0xb084b3e6,0x329ba909,0xb2ce2aad,0xb035b3d3,0x33e529cf,0x292233de,
  0x2d2fb241,0x339230fd,0xb14a2fbd,0xb200b301,0x2d993400,0xb37f1b11,0x2084b36f,0x33ff2deb,0xb2ebb21d,0x3005b129,0x30db339f,0xb25c2cdb,
  0xae5fb3e4,0x3357a93b,0xb190303a,0xb1c0b2cb,0x32453258,0xb0f830e0,0x2c63b2ee,0x33b22ffe,0xb3dfae99,0x29b6b34a,0x2ac633ff,0xb3d2a01f,
  0x339ea438,0x2ce733fc,0xb12eb32c,0x3219af15,0x33b8a78b,0x2c3233f2,0x2810b3b3,0x33ef2c57,0xb2c72e6b,0xb040b354,0x29533400,0xb3e31d1b,
  0x3141b133,0x32093215,0xaf21b39c,0x332aacf3,0xae8d32bd,0xb34cb050,0x317d3290,0xb1d23094,0x27bd33fb,0xb3f1249c,0x2fdd3327,0xb2f72f2c,
  0xaaf7b3e2,0x33cfa96c,0xb099b2c4,0x328cb045,0x2cff33b7,0xb39a2c3e,0x31373250,0xb21130ea,0xae76b378,0x3352adbc,0xb1c9b1cd,0x3186b182,
  0xb3ff1ead,0x1de4b3ff,0xb352adbc,0x2e76b378,0x33f1249c,0xa7bd33fb,0x32f72f2c,0xafdd3327,0xb3cfa96c,0x2af7b3e2,0xb28cb045,0x3099b2c4,
  0x339a2c3e,0xacff33b7,0x321130ea,0xb1373250,0x2953b400,0x33e31d1b,0x33ccadd4,0x2b283373,0xaf21339c,0xb32aacf3,0xb3fb2500,0x246ab3fa,
  0x317db290,0x31d23094,0x337a2ade,0xadb133d0,0xb2f130f3,0xaff3b249,0xb254afd2,0x30e5b2fb,0x339e2438,0xace733fc,0xb12e332c,0xb219af15,
  0xb190b03a,0x31c0b2cb,0x3371b0a8,0x2ddf3281,0x2c6332ee,0xb3b22ffe,0xb3f22829,0x2759b3ef,0x2ac6b3ff,0x33d2a01f,0x32932da5,0xb08e337c,
  0xaf0a33f3,0xb32fa727,0x2406b3b0,0x33fcac6f,0x3347b194,0x2ea431bc,0xb1743359,0xb1daae54,0xb3bc2565,0x2c1ab3f9,0x33eeaf59,0x2842331b,
  0x30ad3089,0xb27e3297,0xb2ceaaad,0x3035b3d3,0xb29ba909,0x3084b3e6,0x305f3030,0xb2b332d1,0x259732e8,0xb3f8300a,0x2ccfb3ed,0x33a1a85b,
  0x31b8b381,0x31992d8d,0xb36c31df,0xadf7b170,0xb3f42d3a,0x26f5b390,0x330423a7,0xafb233fc,0x316bb3d6,0x31e32a7c,0xb3832a01,0x2d81b3dc,
  0xb3bf2c87,0x2c02b3ac,0x28743239,0xb3ec3107,0x2b8931b3,0xb3c6319d,0x3276b35e,0x30b72e3c,0x31f8b3a3,0x31542cc3,0xb33525c9,0x2ef4b3f8,
  0x310c2beb,0xb23533c0,0x33abb267,0x2c9330cc,0x307ab3fe,0x32a2a1b1,0xb06aad76,0x32acb385,0xb3a52d52,0x2cb7b38b,0xb11b33fd,0xb229a2de,
  0x94b63273,0xb40030bc,0x3360aba2,0xae3133c5,0xb2de33a7,0xb01aacab,0xb0c733f6,0xb26b262d,0x30c12a4b,0xb26f33d8,0x32dbaa32,0xb02033d9,
  0x31f0b3f6,0x315d265f,0x2eddb3a9,0x333aac9f,0xb1eb8e48,0x3162b400,0xb3872e1a,0x2d6ab365,0xae25ad5e,0x3363b389,0x8e48b15d,0x3400b1f0,
  0xb3a7333d,0xacabaed2,0xb3f63162,0x262db1eb,0x2a4b301a,0xb3d832de,0xaa32326b,0xb3d930c7,0x33f6b26f,0x265f30c1,0x33a9b020,0xac9f32db,
  0x33c0b368,0x2beb2e0e,0x30cc94b6,0xb2673400,0x21b1b10c,0x33feb235,0x3385b3ab,0x2d762c93,0xb38b307a,0x2d52b2a2,0xa2deb06a,0x33fdb2ac,
  0xb0bc33a5,0xb2732cb7,0xb3c5311b,0x2ba2b229,0x26c32ebb,0xb3f53342,0xb3ac316b,0x2c87b1e3,0x336ab0d1,0xae023264,0xb19d33bf,0xb1b32c02,
  0x3225b3e7,0x311fa8f0,0x2cc32b89,0xb3a333c6,0xaa7cad46,0x33d6b38e,0x33dcb1f8,0xaa013154,0xb3fe3318,0x20e8af64,0x3381b3f8,0x2d8d2597,
  0xb14f335c,0xb1fc2e48,0x2d3ab199,0x3390b1b8,0x29092c7b,0xb3e633ae,0xb03026f5,0x32d1b3f4,0x32e8b084,0xb00a329b,0xb3ed32b3,0x285bb05f,
  0x29cfb005,0x33deb2eb,0xb05a325c,0xb2b630db,0xafbd2922,0x3301b3e5,0x27272b59,0xb3f333c9,0xb36f3200,0x2debb14a,0x31bcaf0a,0xb194332f,
  0xb39f33ff,0xacdba084,0x33f9b347,0xa5652ea4,0x3394b2ba,0xad233055,0xa438a9b6,0x33fcb3df,0x33e4b3f9,0x293b2533,0xb03a2ce7,0x32cbb39e,
  0x3258b357,0x30e0ae5f,0xb2ee31c0,0x2ffeb190,0x2e99b0f8,0x334ab245,0xb3ff33b2,0x201fac63,0xaf4230a3,0xb3213285,0x3133b040,0xb21532c7,
  0xa99e2d17,0xb3e03396,0x32bdb209,0xb0503141,0x278b1f76,0xb3f233ff,0x33b3b34c,0xac572e8d,0x2e6bac32,0xb35433b8,0x3400b3ef,0x1d1b2810,
  0xb289324d,0x309eb0ee,0xb3ce33b5,0x2b0fac4b,0xb2f432c1,0x2fe8b04a,0xb3f033e1,0x27efa985,0xb34f3324,0x2e82af37,0xb3ff33fa,0x1eada4ce,
  0xb3983376,0x2d0badc8,0xb3fb33ff,0xa49c1de4,0x351c35f6,0xac93a617,0xb8a3b93c,0x308d2a16,0x32f43448,0xb160afa5,0xb6a4b7fe,0x353a3389,
  0x2fa53160,0xb448b2f4,0xb389b53a,0x37fe36a4,0x26172c93,0xb5f6b51c,0xaa16b08d,0x393c38a3,0x34c3358c,0xac47a5b2,0xb85fb8f3,0x304229b1,
  0x327e33fd,0xb106af26,0xb63cb785,0x34e7330f,0x2f263106,0xb3fdb27e,0xb30fb4e7,0x3785363c,0x25b22c47,0xb58cb4c3,0xa9b1b042,0x38f3385f,
  0x346a3523,0xabf6a54d,0xb81ab8a8,0x2fef294d,0x3209336b,0xb0acaea7,0xb5d4b70a,0x34933294,0x2ea730ac,0xb36bb209,0xb294b493,0x370a35d4,
  0x254d2bf6,0xb523b46a,0xa94dafef,0x38a8381a,0x341334bc,0xab5fa4e9,0xb7a6b85a,0x2f5928e8,0x319432da,0xb052ae28,0xb56ab68d,0x343e3219,
  0x2e283052,0xb2dab194,0xb219b43e,0x368d356a,0x24e92b5f,0xb4bcb413,0xa8e8af59,0x385a37a6,0x33783456,0xaac8a484,0xb715b80a,0x2ec32884,
  0x3120324a,0xaff2ada9,0xb4ffb60e,0x33d3319e,0x2da92ff2,0xb24ab120,0xb19eb3d3,0x360e34ff,0x24842ac8,0xb456b378,0xa884aec3,0x380a3715,
  0x32cd33e3,0xaa31a420,0xb682b76f,0x2e2d281f,0x30ac31bb,0xaf3fad2a,0xb493b58d,0x33283122,0x2d2a2f3f,0xb1bbb0ac,0xb122b328,0x358d3493,
  0x24202a31,0xb3e3b2cd,0xa81fae2d,0x376f3682,0x3223331c,0xa999a376,0xb5ebb6c6,0x2d972776,0x3039312d,0xae8dacac,0xb426b50b,0x327c30a6,
  0x2cac2e8d,0xb12db039,0xb0a6b27c,0x350b3426,0x23762999,0xb31cb223,0xa776ad97,0x36c635eb,0x317a3257,0xa902a2ad,0xb552b61a,0x2d0026ad,
  0x2f8c309f,0xaddcac2e,0xb371b487,0x31cf3029,0x2c2e2ddc,0xb09faf8c,0xb029b1cf,0x34873371,0x22ad2902,0xb257b17a,0xa6adad00,0x361a3552,
  0x30d23194,0xa86ba1e4,0xb4b7b56a,0x2c6a25e4,0x2ea73012,0xad2aab5f,0xb294b402,0x31222f59,0x2b5f2d2a,0xb012aea7,0xaf59b122,0x34023294,
  0x21e4286b,0xb194b0d2,0xa5e4ac6a,0x356a34b7,0x302c30d2,0xa7a9a11b,0xb41ab4b7,0x2ba7251b,0x2dc22f0c,0xac79aa63,0xb1b6b2f7,0x30742e5f,
  0x2a632c79,0xaf0cadc2,0xae5fb074,0x32f731b6,0x211b27a9,0xb0d2b02c,0xa51baba7,0x34b7341a,0x2f0c3012,0xa67ba052,0xb2f7b402,0x2a7a2452,
  0x2cde2df5,0xab91a967,0xb0d7b1e8,0x2f8b2d65,0x29672b91,0xadf5acde,0xad65af8b,0x31e830d7,0x2052267b,0xb012af0c,0xa452aa7a,0x340232f7,
  0x2dc22ea7,0xa54d9f12,0xb1b6b294,0x294d2311,0x2bf62cde,0xaa31a86b,0xafefb0d7,0x2e2d2c6a,0x286b2a31,0xacdeabf6,0xac6aae2d,0x30d72fef,
  0x1f12254d,0xaea7adc2,0xa311a94d,0x329431b6,0x2c792d2a,0xa4209d7f,0xb074b122,0x281f217f,0x2a312b91,0xa8d0a6e0,0xae2daf8b,0x2cce2ade,
  0x26e028d0,0xab91aa31,0xaadeacce,0x2f8b2e2d,0x1d7f2420,0xad2aac79,0xa17fa81f,0x31223074,0x2a632b5f,0xa1e49bdb,0xae5faf59,0x25e41fdb,
  0x286b2967,0xa6e0a4e9,0xac6aad65,0x2ade28e8,0x24e926e0,0xa967a86b,0xa8e8aade,0x2d652c6a,0x1bdb21e4,0xab5faa63,0x9fdba5e4,0x2f592e5f,
  0x27a9286b,0x9f1298b6,0xaba7ac6a,0x23111cb6,0x254d267b,0xa420a1e4,0xa94daa7a,0x281f25e4,0x21e42420,0xa67ba54d,0xa5e4a81f,0x2a7a294d,
  0x18b61f12,0xa86ba7a9,0x9cb6a311,0x2c6a2ba7,0x211b21e4,0x98b69248,0xa51ba5e4,0x1cb61648,0x1f122052,0x9d7f9bdb,0xa311a452,0x217f1fdb,
  0x1bdb1d7f,0xa0529f12,0x9fdba17f,0x24522311,0x124818b6,0xa1e4a11b,0x96489cb6,0x25e4251b,0xa11ba1e4,0x18b61248,0x251b25e4,0x9cb69648,
  0x9f12a052,0x1d7f1bdb,0x23112452,0xa17f9fdb,0x9bdb9d7f,0x20521f12,0x1fdb217f,0xa452a311,0x924898b6,0x21e4211b,0x16481cb6,0xa5e4a51b,
  0xa7a9a86b,0x1f1218b6,0x2ba72c6a,0xa3119cb6,0xa54da67b,0x242021e4,0x294d2a7a,0xa81fa5e4,0xa1e4a420,0x267b254d,0x25e4281f,0xaa7aa94d,
  0x98b69f12,0x286b27a9,0x1cb62311,0xac6aaba7,0xaa63ab5f,0x21e41bdb,0x2e5f2f59,0xa5e49fdb,0xa86ba967,0x26e024e9,0x2c6a2d65,0xaadea8e8,
  0xa4e9a6e0,0x2967286b,0x28e82ade,0xad65ac6a,0x9bdba1e4,0x2b5f2a63,0x1fdb25e4,0xaf59ae5f,0xac79ad2a,0x24201d7f,0x30743122,0xa81fa17f,
  0xaa31ab91,0x28d026e0,0x2e2d2f8b,0xacceaade,0xa6e0a8d0,0x2b912a31,0x2ade2cce,0xaf8bae2d,0x9d7fa420,0x2d2a2c79,0x217f281f,0xb122b074,
  0xadc2aea7,0x254d1f12,0x31b63294,0xa94da311,0xabf6acde,0x2a31286b,0x2fef30d7,0xae2dac6a,0xa86baa31,0x2cde2bf6,0x2c6a2e2d,0xb0d7afef,
  0x9f12a54d,0x2ea72dc2,0x2311294d,0xb294b1b6,0xaf0cb012,0x267b2052,0x32f73402,0xaa7aa452,0xacdeadf5,0x2b912967,0x30d731e8,0xaf8bad65,
  0xa967ab91,0x2df52cde,0x2d652f8b,0xb1e8b0d7,0xa052a67b,0x30122f0c,0x24522a7a,0xb402b2f7,0xb02cb0d2,0x27a9211b,0x341a34b7,0xaba7a51b,
  0xadc2af0c,0x2c792a63,0x31b632f7,0xb074ae5f,0xaa63ac79,0x2f0c2dc2,0x2e5f3074,0xb2f7b1b6,0xa11ba7a9,0x30d2302c,0x251b2ba7,0xb4b7b41a,
  0xb0d2b194,0x286b21e4,0x34b7356a,0xac6aa5e4,0xaea7b012,0x2d2a2b5f,0x32943402,0xb122af59,0xab5fad2a,0x30122ea7,0x2f593122,0xb402b294,
  0xa1e4a86b,0x319430d2,0x25e42c6a,0xb56ab4b7,0xb17ab257,0x290222ad,0x3552361a,0xad00a6ad,0xaf8cb09f,0x2ddc2c2e,0x33713487,0xb1cfb029,
  0xac2eaddc,0x309f2f8c,0x302931cf,0xb487b371,0xa2ada902,0x3257317a,0x26ad2d00,0xb61ab552,0xb223b31c,0x29992376,0x35eb36c6,0xad97a776,
  0xb039b12d,0x2e8d2cac,0x3426350b,0xb27cb0a6,0xacacae8d,0x312d3039,0x30a6327c,0xb50bb426,0xa376a999,0x331c3223,0x27762d97,0xb6c6b5eb,
  0xb2cdb3e3,0x2a312420,0x3682376f,0xae2da81f,0xb0acb1bb,0x2f3f2d2a,0x3493358d,0xb328b122,0xad2aaf3f,0x31bb30ac,0x31223328,0xb58db493,
  0xa420aa31,0x33e332cd,0x281f2e2d,0xb76fb682,0xb378b456,0x2ac82484,0x3715380a,0xaec3a884,0xb120b24a,0x2ff22da9,0x34ff360e,0xb3d3b19e,
  0xada9aff2,0x324a3120,0x319e33d3,0xb60eb4ff,0xa484aac8,0x34563378,0x28842ec3,0xb80ab715,0xb413b4bc,0x2b5f24e9,0x37a6385a,0xaf59a8e8,
  0xb194b2da,0x30522e28,0x356a368d,0xb43eb219,0xae28b052,0x32da3194,0x3219343e,0xb68db56a,0xa4e9ab5f,0x34bc3413,0x28e82f59,0xb85ab7a6,
  0xb46ab523,0x2bf6254d,0x381a38a8,0xafefa94d,0xb209b36b,0x30ac2ea7,0x35d4370a,0xb493b294,0xaea7b0ac,0x336b3209,0x32943493,0xb70ab5d4,
  0xa54dabf6,0x3523346a,0x294d2fef,0xb8a8b81a,0xb4c3b58c,0x2c4725b2,0x385f38f3,0xb042a9b1,0xb27eb3fd,0x31062f26,0x363c3785,0xb4e7b30f,
  0xaf26b106,0x33fd327e,0x330f34e7,0xb785b63c,0xa5b2ac47,0x358c34c3,0x29b13042,0xb8f3b85f,0xb51cb5f6,0x2c932617,0x38a3393c,0xb08daa16,
  0xb2f4b448,0x31602fa5,0x36a437fe,0xb53ab389,0xafa5b160,0x344832f4,0x3389353a,0xb7feb6a4,0xa617ac93,0x35f6351c,0x2a16308d,0xb93cb8a3,
};
__device__ __align__(128) const uint32_t c_img[2560] = {
  0x326d31ed,0x333b32dd,0x33c33388,0x33fe33ea,0x33c331ed,0x31ed33c3,0xa8b22d64,0xb33bb0c4,0x33ea31ed,0xad64301d,0xb2ddb388,0x315fa8b2,
  0x32dd31ed,0xb3feabc6,0x326dad64,0xad64326d,0x30c431ed,0xaed7b2dd,0x2bc63388,0xa248b3ea,0x2bc631ed,0x315fb3c3,0xb3ea2d64,0x2ed730c4,
  0xa8b231ed,0x3388b01d,0x301db388,0xb1ed28b2,0xb01d31ed,0x22482bc6,0x30c4ad64,0x3388b26d,0x33ea33fe,0x338833c3,0x32dd333b,0x31ed326d,
  0xb2ddb3fe,0xa248b01d,0x326d2ed7,0x338833ea,0x30c433fe,0xb33babc6,0xabc6b33b,0x33fe30c4,0xabc6b3fe,0x31ed32dd,0xb3eaaed7,0x333ba8b2,
  0xa8b233fe,0x2d64b3c3,0xb01d333b,0x315fb26d,0x301db3fe,0xb3fe301d,0x30c42ed7,0x2d64b3ea,0xb26d33fe,0x2ed72bc6,0x33c3b33b,0xa248b0c4,
  0x33c3b3fe,0x315fb2dd,0x28b2aed7,0xaed728b2,0xb0c4b15f,0xaed7b01d,0xabc6ad64,0xa248a8b2,0xabc6b15f,0x315f2bc6,0x33ea3388,0x2ed7326d,
  0x28b2b15f,0x338832dd,0xb01d2d64,0xb1edb3ea,0x301db15f,0x224833c3,0xb0c4b388,0x338830c4,0x326db15f,0xb33b301d,0x33c3ad64,0xb3fe28b2,
  0x33c3b15f,0xb1edabc6,0xa8b23388,0x333bb26d,0x33eab15f,0x2d64b2dd,0xb2dd2d64,0xb15f33ea,0x32ddb15f,0x33feb3c3,0x326db388,0x2d64b0c4,
  0x28b22248,0x2d642bc6,0x301d2ed7,0x315f30c4,0xb01da248,0xb3feb2dd,0xb0c4b33b,0x2d64a8b2,0x326d2248,0x2ed733c3,0xb3c3aed7,0xa248b26d,
  0xb3c3a248,0x315fb01d,0xa8b2333b,0xaed7b3ea,0x33ea2248,0xb388abc6,0x32dd2ed7,0xb1edb0c4,0xb2dda248,0x224832dd,0x326db33b,0xb38828b2,
  0x30c42248,0x333bb3c3,0xabc6aed7,0xb3fe326d,0xabc6a248,0xb1ed301d,0xb3ea333b,0xb33b33ea,0xb26d31ed,0xb33b32dd,0xb3c33388,0xb3fe33ea,
  0xb3c331ed,0xb1ed33c3,0x28b22d64,0x333bb0c4,0xb3ea31ed,0x2d64301d,0x32ddb388,0xb15fa8b2,0xb2dd31ed,0x33feabc6,0xb26dad64,0x2d64326d,
  0xb0c431ed,0x2ed7b2dd,0xabc63388,0x2248b3ea,0xabc631ed,0xb15fb3c3,0x33ea2d64,0xaed730c4,0x28b231ed,0xb388b01d,0xb01db388,0x31ed28b2,
  0x301d31ed,0xa2482bc6,0xb0c4ad64,0xb388b26d,0xb3ea33fe,0xb38833c3,0xb2dd333b,0xb1ed326d,0x32ddb3fe,0x2248b01d,0xb26d2ed7,0xb38833ea,
  0xb0c433fe,0x333babc6,0x2bc6b33b,0xb3fe30c4,0x2bc6b3fe,0xb1ed32dd,0x33eaaed7,0xb33ba8b2,0x28b233fe,0xad64b3c3,0x301d333b,0xb15fb26d,
  0xb01db3fe,0x33fe301d,0xb0c42ed7,0xad64b3ea,0x326d33fe,0xaed72bc6,0xb3c3b33b,0x2248b0c4,0xb3c3b3fe,0xb15fb2dd,0xa8b2aed7,0x2ed728b2,
  0x30c4b15f,0x2ed7b01d,0x2bc6ad64,0x2248a8b2,0x2bc6b15f,0xb15f2bc6,0xb3ea3388,0xaed7326d,0xa8b2b15f,0xb38832dd,0x301d2d64,0x31edb3ea,
  0xb01db15f,0xa24833c3,0x30c4b388,0xb38830c4,0xb26db15f,0x333b301d,0xb3c3ad64,0x33fe28b2,0xb3c3b15f,0x31edabc6,0x28b23388,0xb33bb26d,
  0xb3eab15f,0xad64b2dd,0x32dd2d64,0x315f33ea,0xb2ddb15f,0xb3feb3c3,0xb26db388,0xad64b0c4,0xa8b22248,0xad642bc6,0xb01d2ed7,0xb15f30c4,
  0x301da248,0x33feb2dd,0x30c4b33b,0xad64a8b2,0xb26d2248,0xaed733c3,0x33c3aed7,0x2248b26d,0x33c3a248,0xb15fb01d,0x28b2333b,0x2ed7b3ea,
  0xb3ea2248,0x3388abc6,0xb2dd2ed7,0x31edb0c4,0x32dda248,0xa24832dd,0xb26db33b,0x338828b2,0xb0c42248,0xb33bb3c3,0x2bc6aed7,0x33fe326d,
  0x2bc6a248,0x31ed301d,0x33ea333b,0x333b33ea,0x30c4315f,0x2ed7301d,0x2bc62d64,0x224828b2,0x2bc6315f,0xb15fabc6,0xb3eab388,0xaed7b26d,
  0xa8b2315f,0xb388b2dd,0x301dad64,0x31ed33ea,0xb01d315f,0xa248b3c3,0x30c43388,0xb388b0c4,0xb26d315f,0x333bb01d,0xb3c32d64,0x33fea8b2,
  0xb3c3315f,0x31ed2bc6,0x28b2b388,0xb33b326d,0xb3ea315f,0xad6432dd,0x32ddad64,0x315fb3ea,0xb2dd315f,0xb3fe33c3,0xb26d3388,0xad6430c4,
  0xa8b2a248,0xad64abc6,0xb01daed7,0xb15fb0c4,0x301d2248,0x33fe32dd,0x30c4333b,0xad6428b2,0xb26da248,0xaed7b3c3,0x33c32ed7,0x2248326d,
  0x33c32248,0xb15f301d,0x28b2b33b,0x2ed733ea,0xb3eaa248,0x33882bc6,0xb2ddaed7,0x31ed30c4,0x32dd2248,0xa248b2dd,0xb26d333b,0x3388a8b2,
  0xb0c4a248,0xb33b33c3,0x2bc62ed7,0x33feb26d,0x2bc62248,0x31edb01d,0x33eab33b,0x333bb3ea,0x326d31ed,0x333b32dd,0x33c33388,0x33fe33ea,
  0x33c331ed,0x31ed33c3,0xa8b22d64,0xb33bb0c4,0x33ea31ed,0xad64301d,0xb2ddb388,0x315fa8b2,0x32dd31ed,0xb3feabc6,0x326dad64,0xad64326d,
  0x30c431ed,0xaed7b2dd,0x2bc63388,0xa248b3ea,0x2bc631ed,0x315fb3c3,0xb3ea2d64,0x2ed730c4,0xa8b231ed,0x3388b01d,0x301db388,0xb1ed28b2,
  0xb01d31ed,0x22482bc6,0x30c4ad64,0x3388b26d,0x33ea33fe,0x338833c3,0x32dd333b,0x31ed326d,0xb2ddb3fe,0xa248b01d,0x326d2ed7,0x338833ea,
  0x30c433fe,0xb33babc6,0xabc6b33b,0x33fe30c4,0xabc6b3fe,0x31ed32dd,0xb3eaaed7,0x333ba8b2,0xa8b233fe,0x2d64b3c3,0xb01d333b,0x315fb26d,
  0x301db3fe,0xb3fe301d,0x30c42ed7,0x2d64b3ea,0xb26d33fe,0x2ed72bc6,0x33c3b33b,0xa248b0c4,0x33c3b3fe,0x315fb2dd,0x28b2aed7,0xaed728b2,
  0xb0c4315f,0xaed7301d,0xabc62d64,0xa24828b2,0xabc6315f,0x315fabc6,0x33eab388,0x2ed7b26d,0x28b2315f,0x3388b2dd,0xb01dad64,0xb1ed33ea,
  0x301d315f,0x2248b3c3,0xb0c43388,0x3388b0c4,0x326d315f,0xb33bb01d,0x33c32d64,0xb3fea8b2,0x33c3315f,0xb1ed2bc6,0xa8b2b388,0x333b326d,
  0x33ea315f,0x2d6432dd,0xb2ddad64,0xb15fb3ea,0x32dd315f,0x33fe33c3,0x326d3388,0x2d6430c4,0x28b2a248,0x2d64abc6,0x301daed7,0x315fb0c4,
  0xb01d2248,0xb3fe32dd,0xb0c4333b,0x2d6428b2,0x326da248,0x2ed7b3c3,0xb3c32ed7,0xa248326d,0xb3c32248,0x315f301d,0xa8b2b33b,0xaed733ea,
  0x33eaa248,0xb3882bc6,0x32ddaed7,0xb1ed30c4,0xb2dd2248,0x2248b2dd,0x326d333b,0xb388a8b2,0x30c4a248,0x333b33c3,0xabc62ed7,0xb3feb26d,
  0xabc62248,0xb1edb01d,0xb3eab33b,0xb33bb3ea,0xb26d31ed,0xb33b32dd,0xb3c33388,0xb3fe33ea,0xb3c331ed,0xb1ed33c3,0x28b22d64,0x333bb0c4,
  0xb3ea31ed,0x2d64301d,0x32ddb388,0xb15fa8b2,0xb2dd31ed,0x33feabc6,0xb26dad64,0x2d64326d,0xb0c431ed,0x2ed7b2dd,0xabc63388,0x2248b3ea,
  0xabc631ed,0xb15fb3c3,0x33ea2d64,0xaed730c4,0x28b231ed,0xb388b01d,0xb01db388,0x31ed28b2,0x301d31ed,0xa2482bc6,0xb0c4ad64,0xb388b26d,
  0xb3ea33fe,0xb38833c3,0xb2dd333b,0xb1ed326d,0x32ddb3fe,0x2248b01d,0xb26d2ed7,0xb38833ea,0xb0c433fe,0x333babc6,0x2bc6b33b,0xb3fe30c4,
  0x2bc6b3fe,0xb1ed32dd,0x33eaaed7,0xb33ba8b2,0x28b233fe,0xad64b3c3,0x301d333b,0xb15fb26d,0xb01db3fe,0x33fe301d,0xb0c42ed7,0xad64b3ea,
  0x326d33fe,0xaed72bc6,0xb3c3b33b,0x2248b0c4,0xb3c3b3fe,0xb15fb2dd,0xa8b2aed7,0x2ed728b2,0x29ed29ed,0x29ed29ed,0x29ed29ed,0x29ed29ed,
  0x2bc32a6d,0x2add2bea,0x23c628c4,0xa81da0b2,0x2bc32add,0xa3c6281d,0xabc3aadd,0x23c6a81d,0x29ed2b3b,0xabfea564,0x295fa6d7,0x1a482b88,
  0x25642b88,0xa564ab88,0x25642b88,0xa564ab88,0xa0b22bc3,0x2a6daadd,0xabea23c6,0x28c4281d,0xa8c42bea,0x2a6da0b2,0x28c4abea,0xaa6d20b2,
  0xab3b2bfe,0xa564295f,0x26d79a48,0x2b88a9ed,0x29ed29ed,0x29ed29ed,0x29ed29ed,0x29ed29ed,0xabc3aa6d,0xaaddabea,0xa3c6a8c4,0x281d20b2,
  0x2bc32add,0xa3c6281d,0xabc3aadd,0x23c6a81d,0xa9edab3b,0x2bfe2564,0xa95f26d7,0x9a48ab88,0x25642b88,0xa564ab88,0x25642b88,0xa564ab88,
  0x20b2abc3,0xaa6d2add,0x2beaa3c6,0xa8c4a81d,0xa8c42bea,0x2a6da0b2,0x28c4abea,0xaa6d20b2,0x2b3babfe,0x2564a95f,0xa6d71a48,0xab8829ed,
  0x295f295f,0x295f295f,0x295f295f,0x295f295f,0x23c628c4,0xa81da0b2,0xabc3aa6d,0xaaddabea,0xa3c6281d,0xabc3aadd,0x23c6a81d,0x2bc32add,
  0xa95f26d7,0x9a48ab88,0x29ed2b3b,0xabfea564,0xab882564,0x2b88a564,0xab882564,0x2b88a564,0xabea23c6,0x28c4281d,0x20b2abc3,0xaa6d2add,
  0xaa6d20b2,0xa8c42bea,0x2a6da0b2,0x28c4abea,0xa6d71a48,0xab8829ed,0xab3b2bfe,0xa564295f,0x295f295f,0x295f295f,0x295f295f,0x295f295f,
  0xa3c6a8c4,0x281d20b2,0x2bc32a6d,0x2add2bea,0xa3c6281d,0xabc3aadd,0x23c6a81d,0x2bc32add,0x295fa6d7,0x1a482b88,0xa9edab3b,0x2bfe2564,
  0xab882564,0x2b88a564,0xab882564,0x2b88a564,0x2beaa3c6,0xa8c4a81d,0xa0b22bc3,0x2a6daadd,0xaa6d20b2,0xa8c42bea,0x2a6da0b2,0x28c4abea,
  0x26d79a48,0x2b88a9ed,0x2b3babfe,0x2564a95f,0xabfe2bfe,0xabfe2bfe,0xabfe2bfe,0xabfe2bfe,0xaadd2bea,0xa3c628c4,0x281da0b2,0x2bc3aa6d,
  0xa81d2bc3,0x2adda3c6,0x281dabc3,0xaadd23c6,0x9a482b88,0x29edab3b,0xabfe2564,0x295f26d7,0x26d72b3b,0xa6d7ab3b,0x26d72b3b,0xa6d7ab3b,
  0x2a6d2add,0xabeaa3c6,0x28c4a81d,0x20b22bc3,0x2bea2a6d,0xa0b228c4,0xabeaaa6d,0x20b2a8c4,0x2b8829ed,0x2b3b2bfe,0x2564295f,0xa6d79a48,
  0xabfe2bfe,0xabfe2bfe,0xabfe2bfe,0xabfe2bfe,0x2addabea,0x23c6a8c4,0xa81d20b2,0xabc32a6d,0xa81d2bc3,0x2adda3c6,0x281dabc3,0xaadd23c6,
  0x1a48ab88,0xa9ed2b3b,0x2bfea564,0xa95fa6d7,0x26d72b3b,0xa6d7ab3b,0x26d72b3b,0xa6d7ab3b,0xaa6daadd,0x2bea23c6,0xa8c4281d,0xa0b2abc3,
  0x2bea2a6d,0xa0b228c4,0xabeaaa6d,0x20b2a8c4,0xab88a9ed,0xab3babfe,0xa564a95f,0x26d71a48,0x1a489a48,0x1a489a48,0x1a489a48,0x1a489a48,
  0x281da0b2,0x2bc3aa6d,0x2addabea,0x23c6a8c4,0x2adda3c6,0x281dabc3,0xaadd23c6,0xa81d2bc3,0x2bfea564,0xa95fa6d7,0x9a482b88,0x29edab3b,
  0x2b3ba6d7,0xab3b26d7,0x2b3ba6d7,0xab3b26d7,0x28c4a81d,0x20b22bc3,0xaa6daadd,0x2bea23c6,0x20b2a8c4,0x2bea2a6d,0xa0b228c4,0xabeaaa6d,
  0xa564a95f,0x26d71a48,0x2b8829ed,0x2b3b2bfe,0x1a489a48,0x1a489a48,0x1a489a48,0x1a489a48,0xa81d20b2,0xabc32a6d,0xaadd2bea,0xa3c628c4,
  0x2adda3c6,0x281dabc3,0xaadd23c6,0xa81d2bc3,0xabfe2564,0x295f26d7,0x1a48ab88,0xa9ed2b3b,0x2b3ba6d7,0xab3b26d7,0x2b3ba6d7,0xab3b26d7,
  0xa8c4281d,0xa0b2abc3,0x2a6d2add,0xabeaa3c6,0x20b2a8c4,0x2bea2a6d,0xa0b228c4,0xabeaaa6d,0x2564295f,0xa6d79a48,0xab88a9ed,0xab3babfe,
  0xa95fa95f,0xa95fa95f,0xa95fa95f,0xa95fa95f,0xa3c6a8c4,0x281d20b2,0x2bc32a6d,0x2add2bea,0x23c6a81d,0x2bc32add,0xa3c6281d,0xabc3aadd,
  0x295fa6d7,0x1a482b88,0xa9edab3b,0x2bfe2564,0x2b88a564,0xab882564,0x2b88a564,0xab882564,0x2beaa3c6,0xa8c4a81d,0xa0b22bc3,0x2a6daadd,
  0x2a6da0b2,0x28c4abea,0xaa6d20b2,0xa8c42bea,0x26d79a48,0x2b88a9ed,0x2b3babfe,0x2564a95f,0xa95fa95f,0xa95fa95f,0xa95fa95f,0xa95fa95f,
  0x23c628c4,0xa81da0b2,0xabc3aa6d,0xaaddabea,0x23c6a81d,0x2bc32add,0xa3c6281d,0xabc3aadd,0xa95f26d7,0x9a48ab88,0x29ed2b3b,0xabfea564,
  0x2b88a564,0xab882564,0x2b88a564,0xab882564,0xabea23c6,0x28c4281d,0x20b2abc3,0xaa6d2add,0x2a6da0b2,0x28c4abea,0xaa6d20b2,0xa8c42bea,
  0xa6d71a48,0xab8829ed,0xab3b2bfe,0xa564295f,0x29ed29ed,0x29ed29ed,0x29ed29ed,0x29ed29ed,0x2bc32a6d,0x2add2bea,0x23c628c4,0xa81da0b2,
  0x2bc32add,0xa3c6281d,0xabc3aadd,0x23c6a81d,0x29ed2b3b,0xabfea564,0x295fa6d7,0x1a482b88,0x25642b88,0xa564ab88,0x25642b88,0xa564ab88,
  0xa0b22bc3,0x2a6daadd,0xabea23c6,0x28c4281d,0xa8c42bea,0x2a6da0b2,0x28c4abea,0xaa6d20b2,0xab3b2bfe,0xa564295f,0x26d79a48,0x2b88a9ed,
  0x29ed29ed,0x29ed29ed,0x29ed29ed,0x29ed29ed,0xabc3aa6d,0xaaddabea,0xa3c6a8c4,0x281d20b2,0x2bc32add,0xa3c6281d,0xabc3aadd,0x23c6a81d,
  0xa9edab3b,0x2bfe2564,0xa95f26d7,0x9a48ab88,0x25642b88,0xa564ab88,0x25642b88,0xa564ab88,0x20b2abc3,0xaa6d2add,0x2beaa3c6,0xa8c4a81d,
  0xa8c42bea,0x2a6da0b2,0x28c4abea,0xaa6d20b2,0x2b3babfe,0x2564a95f,0xa6d71a48,0xab8829ed,0x9a481a48,0x9a481a48,0x9a481a48,0x9a481a48,
  0xa81d20b2,0xabc32a6d,0xaadd2bea,0xa3c628c4,0xaadd23c6,0xa81d2bc3,0x2adda3c6,0x281dabc3,0xabfe2564,0x295f26d7,0x1a48ab88,0xa9ed2b3b,
  0xab3b26d7,0x2b3ba6d7,0xab3b26d7,0x2b3ba6d7,0xa8c4281d,0xa0b2abc3,0x2a6d2add,0xabeaa3c6,0xa0b228c4,0xabeaaa6d,0x20b2a8c4,0x2bea2a6d,
  0x2564295f,0xa6d79a48,0xab88a9ed,0xab3babfe,0x9a481a48,0x9a481a48,0x9a481a48,0x9a481a48,0x281da0b2,0x2bc3aa6d,0x2addabea,0x23c6a8c4,
  0xaadd23c6,0xa81d2bc3,0x2adda3c6,0x281dabc3,0x2bfea564,0xa95fa6d7,0x9a482b88,0x29edab3b,0xab3b26d7,0x2b3ba6d7,0xab3b26d7,0x2b3ba6d7,
  0x28c4a81d,0x20b22bc3,0xaa6daadd,0x2bea23c6,0xa0b228c4,0xabeaaa6d,0x20b2a8c4,0x2bea2a6d,0xa564a95f,0x26d71a48,0x2b8829ed,0x2b3b2bfe,
  0xabfe2bfe,0xabfe2bfe,0xabfe2bfe,0xabfe2bfe,0xaadd2bea,0xa3c628c4,0x281da0b2,0x2bc3aa6d,0xa81d2bc3,0x2adda3c6,0x281dabc3,0xaadd23c6,
  0x9a482b88,0x29edab3b,0xabfe2564,0x295f26d7,0x26d72b3b,0xa6d7ab3b,0x26d72b3b,0xa6d7ab3b,0x2a6d2add,0xabeaa3c6,0x28c4a81d,0x20b22bc3,
  0x2bea2a6d,0xa0b228c4,0xabeaaa6d,0x20b2a8c4,0x2b8829ed,0x2b3b2bfe,0x2564295f,0xa6d79a48,0xabfe2bfe,0xabfe2bfe,0xabfe2bfe,0xabfe2bfe,
  0x2addabea,0x23c6a8c4,0xa81d20b2,0xabc32a6d,0xa81d2bc3,0x2adda3c6,0x281dabc3,0xaadd23c6,0x1a48ab88,0xa9ed2b3b,0x2bfea564,0xa95fa6d7,
  0x26d72b3b,0xa6d7ab3b,0x26d72b3b,0xa6d7ab3b,0xaa6daadd,0x2bea23c6,0xa8c4281d,0xa0b2abc3,0x2bea2a6d,0xa0b228c4,0xabeaaa6d,0x20b2a8c4,
  0xab88a9ed,0xab3babfe,0xa564a95f,0x26d71a48,0x3bfb3bff,0x3be53bf2,0x3bbf3bd4,0x3b873ba5,0x3bd03bfb,0x3b013b7c,0x399d3a60,0x378538bc,
  0x35173b52,0xbbc9b7c8,0xb074ba9b,0x3bfe391b,0x319e3b27,0xbbf3b979,0x363cb80a,0x3a2d3bc5,0xba093986,0x3a7eb8f8,0xbae5385f,0x3b3db77a,
  0xbabd393c,0x3bb0b699,0xbc00305b,0x3ba730d7,0xbb2a35c8,0xb8353bb2,0x3a64b1e8,0x3962bbf7,0xba90350b,0xba413bff,0x3602340e,0x3bf6bad8,
  0xac6aa5e4,0xb122af59,0xb402b294,0xb56ab4b7,0xb2deac9c,0xb7bdb5a5,0xb9b3b8d6,0xbb10ba73,0xbb96b676,0xb359bafe,0x3bec3884,0x2a163a29,
  0xbbe0b72c,0x2f27b9d6,0x3b5e3ae8,0xb91633a2,0xb941b9c9,0x38ad3a45,0xb80fbab3,0x36d23b13,0xb850ba0d,0x346f3b4a,0x1fdbbbed,0xb4ab3be8,
  0x3721bb76,0xbace3463,0xb8d13bdd,0x39ebadfb,0x3894bb98,0xb8fd281f,0xbb6a3bbd,0x2e2d3825,0x3b3f3b65,0x3ae83b16,0x3a813ab6,0x3a0d3a49,
  0x3263356a,0xad972b43,0xb5dfb359,0xb8eeb7f3,0xa9b139aa,0xbbedba25,0x3340b889,0x3b983afb,0xbaa2aa16,0xb4cfbb8e,0x3c0038ad,0xb44b38e5,
  0xbb853625,0x3bbdb4c3,0xbbe432ad,0x3bfbaf8b,0xbaacb6d2,0x39243954,0xb65fbace,0x2fbd3bb8,0xb9661648,0xba603bf8,0x383a31cf,0x3b27bbb3,
  0x3219b9eb,0xbb1836f4,0xb9903be5,0x37dd3010,0xb6c6b61a,0xb80ab76f,0xb8a8b85a,0xb93cb8f3,0xbbd7bb87,0xbbf8bbfd,0xbb71bbc9,0xba4dbaf1,
  0xbbfeb9a6,0x305bb91f,0x3bcb3a97,0xb50b37d2,0xb87abbfe,0x3ba13546,0x24523a7e,0xbbb5ba54,0xb576bb63,0x340e3ba3,0xb13bbbd3,0x2c9c3bf2,
  0x386abb3d,0xba2139f8,0x3b57b835,0xbbf13432,0x39e7bc00,0xb8d6adc9,0xbacb3bde,0x372c3457,0x3bdab962,0x3764bb35,0xb9c03122,0xbaf73bef,
  0x398b39cd,0x38fd3946,0x386538b2,0x37853815,0xba85b9c9,0xbb92bb1e,0xbbfebbdd,0xbbc2bbf5,0xb66b3682,0xbb01bb94,0x387fb371,0x3a2d3beb,
  0xbac7bb76,0x3a00ad33,0x36bb3bd4,0xbbeab79b,0xbc0026ad,0x3bf32c38,0xbbd6b109,0x3ba733eb,0x3153bbff,0xb70a3b9e,0x396bba9b,0xbade390c,
  0xb5d4b5bc,0xbbb03b2c,0x32013830,0x3bf6ba67,0x3bccbb52,0x2c06b92e,0xbb83385f,0xb8c73bab,0xb9c5b982,0xba41ba04,0xbab0ba7a,0xbb10bae1,
  0xb8a3b986,0xb52fb74e,0xa94db1e8,0x33d32e91,0xbb54bb4f,0x37bdb523,0x3a9e3bc8,0xb916308d,0x3840b5c8,0x394a3bf9,0xbb42b294,0xb0a6bb0a,
  0x251bbbff,0xaf273bfc,0x327cbbe6,0xb4ab3bc0,0x3be325e4,0xbb2fb4e7,0x39e33884,0xb81aba35,0x3b73bb78,0xb46fb715,0xbbdc3ad1,0x2e2d38cc,
  0x33283676,0x3bfcba19,0x3581bab3,0xba6b3493,0x363136dd,0x34cf3581,0x32c6341a,0x2fbd3153,0xbae1bb65,0xb970ba39,0xb715b889,0xb16cb4f3,
  0xb9a12a7a,0xb924bbfe,0x3a933042,0x37dd3bcc,0x308db9aa,0x3b453b07,0xb94632ad,0xb845bbfa,0xbb68b55e,0x3b1836bb,0xbabab805,0x3a4d38a3,
  0x3bc0b625,0xbbfe2ec3,0x3b9431cf,0xba89b742,0x9cb6b95d,0xbbf8396b,0xb1b63a5c,0x3bb5b840,0x38cc9648,0x3b81bbac,0xac38b85a,0xbbce3933,
  0xbb60bb3a,0xbba1bb83,0xbbd2bbbc,0xbbf1bbe3,0x3815361a,0x39df3907,0x3b2c3a97,0x3be23b9c,0xb9afbbfd,0x3a21294d,0x388e3bee,0xbaf7b328,
  0x3beb39a6,0xb6af37a6,0xba04bbd3,0x3ac42d00,0x360ebb89,0xb7643b42,0x3855baeb,0xb8ee3a85,0x33eb3b63,0x28e8bbf5,0xb5233bde,0x389ebb21,
  0x3c00b9f0,0x2d97b9e3,0xbbdf38db,0xb44b3ac7,0xba673c00,0x358d3487,0x3bfcbab6,0x330fba15,0x3b7a3bf1,0x394a3a93,0x33893764,0xb3d39cb6,
  0x3afb3be2,0x35eb3946,0xb4c328e8,0xbaa9b8cc,0x27763af7,0xbb2fbaba,0x3a76ad97,0x30a63b60,0xaf8b3ac4,0xb994bb94,0x3bf8358d,0xb8743815,
  0xbb4c38ee,0x3bfcb1b6,0xbad5b4cf,0x381a39af,0xbbb3389e,0x3b592c38,0xb76fb970,0xb24b3beb,0xb9d2344b,0xbb923bd2,0xb0f03924,0x3a6bb60e,
  0xb8f3330f,0xbc003b2c,0xb91f3b45,0x323233eb,0xb5b1afbd,0xba00b88e,0xbbc6bb18,0xbbc2bc00,0xb7d2b16c,0xbb6fba04,0xbba3bbfe,0xb86fba67,
  0xbbffb7dd,0x370ab855,0x38b73bf8,0xbbeab631,0xbbf2b845,0x39bcb523,0x2dc93b81,0xbaa5bae1,0xb68dba4d,0xac063bdf,0x382abba1,0xbade39a1,
  0xb457ba89,0xb6543bfc,0x3b16b9df,0xbbd8308d,0x397dbbb5,0xb52fb2c6,0xbbe73a21,0xb8c73b68,0x3a49bbce,0x2311b715,0xba2536af,0xbbd93bc0,
  0xb958b785,0xbb81ba9e,0xbbefbbf3,0xba89bb73,0xbbf7bbc2,0xb9b8bb42,0xaf59b70a,0x384a3328,0xbb8bba2d,0x39dfb27c,0x34263bb0,0xbbceb98b,
  0xb4b7bbea,0x3b6c39e3,0xbafe2c06,0x3185ba85,0xaadebba7,0xb6af3bdc,0x3a58ba41,0xbbe2366b,0x3a29bade,0xbc003581,0x3a45352f,0xb2f7bac7,
  0x3b37bbf6,0x28e8b865,0xbaee37bd,0xbac43c00,0x3b13b8c7,0x3b5cbbfe,0x3463b94a,0xb8993153,0xb9f4bb10,0xb58db87f,0x3029af27,0x389e35d4,
  0x2dfbb3d3,0x399936bb,0x3bf23b2f,0x3ac13bcc,0x3552b916,0x39703bd6,0xbbbab46f,0x330fb9c5,0x3ba530a6,0xb5f7396b,0xb7c8bbfc,0x3be138a3,
  0x3bfdb4ab,0xbb45b201,0x38e038fd,0xb16cbb54,0x391b381a,0xa17fbb83,0xb8f83b92,0x3bcfb840,0x36e82e2d,0x3bfebab0,0x37febb01,0xb845251b,
  0xb77a3a6b,0x3648294d,0x3bb2ba00,0x3a8cbbe3,0xb742b93c,0x2311b340,0x37a6340e,0x3aa93966,0x3b963a4d,0x3b7f3c00,0x380f3a21,0xb0be3219,
  0x3933b50b,0x35eb3be4,0xbbf5b8d6,0x3874b6c6,0x39413bb5,0xbbffb65f,0x38d1b764,0x33ba3bd7,0x3b9c2c9c,0xb994b83a,0x34873ae8,0x324bbbfe,
  0xb7213bf1,0x3b47b990,0xbbbf2d97,0x38c1387a,0x2d00372c,0x3b59b8a8,0x3a39bbed,0xb232b576,0xbbfb3af7,0xb9743b71,0x307434cf,0x3adbb86a,
  0x3b213a0d,0x3c003bcb,0x3b073bbd,0x386f39e7,0x351738ee,0xb599a452,0xbae5b924,0xbbe9bbda,0x3a153b98,0xbb6fb13b,0x2ec3ba60,0x3aa53b3f,
  0xba09344b,0xa884bb57,0x3a643b18,0xbbc3b263,0xb4f33bfb,0x39bcbacb,0xbbac380a,0x3bd8a9b1,0xbb2aafbd,0x36a439c0,0x3402bbf8,0xba6f3aa2,
  0xbbfa3b27,0xb6543a81,0x3907b05b,0x3bd9bb85,0x2c6ab7dd,0xb9da35df,0xbbec3ba1,0xb8203aac,0x3bf53b87,0x3b6c3bec,0x392e3a7e,0x32f73721,
  0xb9e7b785,0xbbfcbb5e,0xba81bbb0,0xb43eb894,0x379b3bfe,0xbc00b80f,0x374eb835,0x38993bfb,0xbb3fba2d,0x3b329fdb,0xb3403a41,0xb8eabbd0,
  0xb90c3b3d,0x3b5cb8d1,0xbbf93122,0x3ac13517,0x29b1bba7,0xb94f3b6a,0x3be4b7bd,0xbaf4b19e,0xbbab3962,0xb9993bbf,0x34e73359,0x3be1ba09,
  0x3b85bbf6,0x353ab99d,0xb83a2f27,0xbbf03abd,0x2e91356a,0xb5f7b074,0xba19b8ad,0xbbcfbb2a,0xb966bb10,0xaba7b63c,0x38a8346f,0x3bb73a90,
  0xbb0aaa16,0xa17fbae5,0x3b1e3ace,0xba8c2c6a,0x36c6b916,0x36ff3c00,0xbbcbb8fd,0x3a50b2de,0xba35b6d2,0x36483a64,0x2d33bbe5,0xb84a3b96,
  0x3bfeb4ab,0xb9fcb602,0x313b3b01,0x37e8bbe0,0x3493b9eb,0xb9b83402,0xbb9e3bc9,0xb1853941,0x35762e2d,0x3b90b9b3,0x3acbbbf3,0x2fefb850,
  0x3a543bcf,0x2884374e,0xb9f8b648,0xbbe9bbab,0x398b3bb7,0xb4db3340,0xbbdcb9fc,0xb911bb85,0xb4323a8c,0xb6a4bbf9,0x3b3539b8,0xbbc3ae91,
  0xb66b3a50,0xad65bbe4,0x38653b90,0xbb0db966,0xbbef384a,0x39da34e7,0x2b43bb6c,0xba6f3b0a,0xbc0037e8,0x3759383a,0x387fbbfc,0xbbf636c6,
  0xb7f33185,0xbb7f3a19,0xbb8e3c00,0xb8203a35,0xb5d42fef,0xba1d38a8,0xbbd63b32,0xbba93bfe,0xb8e5b2f7,0xbbffbb1e,0xb954bb5c,0x30beb493,
  0xb9c5b43e,0xbb9fbbcb,0xb201b94f,0x3a313576,0xbbb8b899,0x3b47ad33,0xb6f43999,0xb3babbf5,0xbb54b8ea,0x3bf9313b,0xbab0353a,0x3790b9e7,
  0xb010bac1,0xb9743b9e,0x3bfdb5f7,0xb8c1b79b,0x251bbaf4,0xbb1b3acb,0x3a9e2ba7,0x2e5fbb3f,0x3af1bbe1,0x3599b92e,0xb546a17f,0xbadb390c,
  0x3b73bbf0,0x3929ba81,0x327cb6ff,0xb49f29b1,0xb825baa9,0x353aaec3,0x3b7c3994,0x3af43bfa,0x360eb0be,0x3bf43a64,0x388e3b47,0xb7372c6a,
  0x38bcb874,0x2ba73bac,0xb979bb59,0x3bf03742,0x3c0033ba,0xbb043402,0x3855b974,0xacce3b96,0x3bc5b24b,0xb6ffb907,0xb6993c00,0x3bb7b933,
  0x363138c1,0x3902bbec,0xbbdf3599,0x34ff3941,0x30d73232,0x39fcb7a6,0x3bffbb6f,0x3a50bb9c,0xb9a13adb,0xb47b380f,0x32c62884,0x3937b721,
  0x3ad8386f,0x3b903bf5,0x35a539bc,0xb7e8ad00,0x3b683be9,0x2ef538d1,0xba93b6a4,0xbb24bbfb,0x3a733aa5,0xbbfcb487,0x39d6b654,0xafef3b21,
  0x1cb63bc3,0xb7b2bbbf,0x3aba39da,0xbbfab517,0xb3a23bd8,0x3b32ba39,0xbb4a2311,0x343e3a15,0xbb603a6f,0x3a3d3074,0x31b6bb7f,0xbb9a3a09,
  0xbbe83bd9,0xb94f3b07,0xa81f35eb,0x38eab4f3,0xb9af3820,0xbbae3ae5,0xbbd23bff,0xba113b2a,0x319e389e,0xb929b426,0xbc00bb45,0xb911bb37,
  0xbbffbac1,0xb805bafe,0x382a217f,0x3bfd3b13,0xbabd330f,0x34dbba58,0x36023bfe,0xbb0db9f4,0xb68dbbe1,0x3a5c3a45,0xbbe7b648,0x3b89adfb,
  0xba90b16c,0x2d653aee,0x39b3bb81,0xbbf63552,0x397dbbcf,0xbbbc3463,0x338939b8,0x39f0bba5,0x32deb845,0xb7593029,0xbb5e39df,0xbba93bfd,
  0x3b7aba8c,0x3beebbf2,0x3a76bb6c,0x36ddb91b,0xbbe0ba89,0xba1dbbba,0x1fdbb6af,0x3a3136e8,0xa776b84a,0x3aeb37c8,0x3ad53c00,0xaa7a377a,
  0xb850bbce,0x3b9f38e0,0xbb6a28e8,0x3790b958,0x3b4cb185,0xb8db38f8,0x30f0bb5c,0x355e3bf7,0x3894bbe2,0xbbf937fe,0x399d358d,0x2e5fbb8b,
  0x39d232f7,0x341abbb2,0xbbc63999,0x395d34b7,0x3bd0bac4,0x3b1bbbef,0x363cb970,0xb49faade,0xb5b13899,0x30422f59,0x38b7b5f7,0x3b3aba29,
  0x3219b3d3,0x3b0438b7,0x3b713bfc,0x34ff397d,0x36e83aa9,0xb8b2adc9,0xbbefbb59,0xb5bcba49,0x3bd730a6,0xb902382a,0xa452bb92,0x39373b7a,
  0xb9583874,0x3371bb16,0x34263c00,0xb982bafb,0x387a381a,0x347bbbe7,0xbb573a00,0x3b242776,0xbb8b324b,0x31093a25,0x3a58bb6f,0xbb4f2f8b,
  0xb86a3a6b,0x2ef53389,0x39c0b70a,0x3bfabb4c,0xaadeb232,0xb83034c3,0xbaee39bc,0xbbff3bb3,0x3bda3bc2,0x37b23a76,0xb5df2c06,0xbb9ab9d2,
  0xbb37b86f,0xba7abbf8,0x3029b654,0x3b7838f3,0x32633bea,0xba3dbad5,0x3c00352f,0xba1135b1,0xb9f4baa5,0x3bc8376f,0xbbba2311,0x39cdb7d2,
  0xbaa23ade,0x3baeb0f0,0xb65fb94a,0xb7373bff,0x3552bbd8,0xbbe6391f,0x38e035eb,0x3682bbf2,0xbaac38c7,0xbbf43bc6,0xb9903b2f,0xacce368d,
  0x3bfdbbd9,0x3ad1bba3,0x37feb994,0x26adb457,0x38a33b9a,0xb8dba452,0xbb83bbae,0x2a7ab86a,0x37423b78,0xbab6b426,0xb907bbe6,0x39aa2ade,
  0xb8403a11,0x341abb57,0x294d3bf4,0xb55ebbda,0xb93339cd,0x3889ba58,0xb7a63ad1,0x3625bb37,0xbbe33737,0x304239c0,0x3b42bb04,0xb95db263,
  0xbb9c3682,0xb2ad3aee,0x3bf5b8b2,0x1648b9f4,0xb3282cce,0xb80535df,0xb9e33902,0xbb3a3aa2,0xad0026ad,0xb1cf3029,0xb4873371,0xb61a3552,
  0xba85b4ff,0xba5cbc00,0x3581b47b,0x3bfd3aac,0xbb21b5bc,0xb85abbba,0x3a393109,0x39a63bfd,0xbac7b937,0x3bbc365f,0xbbfeaef5,0x3b89b219,
  0xba15b982,0x3a9738e0,0xbb07b830,0x3b6336e8,0x3153bb24,0xbbee3990,0x36bb37b2,0x39f0bbd7,0x34f3bb4f,0xbbd337fe,0xaec33a7a,0x3c00b958,
  0x3bccbbfa,0x3aebbb71,0x396bba3d,0x36ddb87a,0x3bfabbff,0x3bdebbef,0x3bacbbc8,0x3b65bb8b,0x3bc03911,0x38303b6a,0xb946ad65,0xbb4fbbd0,
  0x3a353bfd,0xb85f30f0,0xbb1ebbbc,0x35c8b5b1,0x38cc3b0d,0xba7ab99d,0x3b943759,0xbbffb19e,0xb4933b89,0x31e8bbc6,0xad333bee,0xa5e4bbff,
  0xb8153bf6,0x3bc8b63c,0xac38ba1d,0xbb783abd,0xbbf539f0,0x329438b7,0x3b9ebaeb,0xb676b68d,0xbbeb3ba9,0xbbe63c00,0xbb2c3b9f,0xb9cd3a90,
  0xb79b36dd,0xb884382a,0xb92e38db,0xb9c9397d,0x33eb3a31,0xbad1b602,0xba04bbf9,0x3682b2de,0xb90c2a7a,0xbab3bbe7,0x374eb41a,0x3b763b7a,
  0xba673790,0x38b2b9b3,0xb5233b1b,0x26adbbe0,0xbbabb55e,0x3bdd3389,0xbbf9b042,0x3bff2776,0xbae12e5f,0xb3713b5e,0x3bfcb929,0xb5bcb850,
  0xae91b95d,0xbbd43a76,0x34e73805,0x3b52bb4c,0x308db49f,0xb1091fdb,0xb71534db,0xb9823894,0x3b0abb3a,0x3a9bbad5,0x3a19ba5c,0x3986b9d2,
  0x2f8bb7e8,0x3bde3979,0x376f3b32,0xb9aab0d7,0x3bb83b24,0xb1223855,0xbbfdba3d,0xaa16b9a1,0x3bb3afef,0xbab63699,0x391fb94f,0xb6253ad8,
  0x30103bfa,0xb359bbdf,0x35463bae,0xb6d2bb68,0x38f3343e,0x3889bbff,0xbba3353a,0x96483a73,0xbaf13b9a,0x38ad32c6,0x39f8bbf4,0xb9eb9cb6,
  0xb7d238ea,0xb2ad35a5,0x2dc92ba7,0x361ab3a2,0xba543a11,0xbace3a93,0xbb353b04,0xbb873b60,0x3bf23af4,0x31cf39d6,0xbb16b6ff,0xb9a6bbe8,
  0xb4323737,0xbbe5baba,0x2b43b902,0x3bfe39af,0x34573bf0,0xb85abb4a,0x3a2539fc,0xbb63b825,0xbbef2cce,0x3bc9b1b6,0xbb8e347b,0x3b3db60e,
  0xba493bb7,0x3a97a81f,0x34c3bb90,0xbc0038bc,0xb7f3b4ff,0xba7e3bd2,0x39542ef5,0x3962bc00,0xbafb3a50,0xbbd33b7c,0xbbf83bfc,0xbb653bc5,
  0x38e5b937,0x3835b88e,0x36f4b7b2,0x356ab631,0xbb13bbe9,0x31e8b6f4,0x3bf239da,0x36763af1,0x3be83911,0x340e3ab0,0xbb7cb759,0xb72cbb73,
  0x2dfbbbc3,0x32943bfd,0xb7c8bb7f,0x39c93a54,0x38253b0d,0xb8d6ba9e,0x39793a1d,0xba0db98b,0x3ba5ba6f,0xb884b546,0xb8f83bff,0x3b76b432,
  0xb8bc3bf6,0x3ae8b27c,0x3699bb9f,0xbb98366b,0x391bb820,0x3ab3b9f8,0x3bb2bb47,0x3bffbbef,0xbbc53ba9,0xbbed3bdc,0xbbff3bf9,0xbbfb3c00,
  0x377ab0be,0x3bdd3b35,0x2f593974,0xbb52b7f3,0x30d73a31,0xbbbdb865,0xb5a5bb1b,0x3b2735d4,0x3bf733ba,0xbbd42b43,0x3afeb599,0xb98638e5,
  0xbad83790,0x3a60b87f,0xb9d63929,0x393cb9c5,0x34b738c1,0x3a9bbb8e,0xba45a884,0xb5c83bb8,0xba732e5f,0xb80a3bd6,0x3b4ab4db,0x350bbb54,
  0xba293adb,0xb85f3954,0xb46336a4,0x25e43010,0x33a2b49f,0x305bb201,0x281fad65,0xac9c251b,0x3f803f80,0x3f803f80,0x3f803f80,0x3f803f80,
  0x3f803f80,0x3f803f80,0x3f803f80,0x3f803f80,0x3f803f80,0x3f803f80,0x3f803f80,0x3f803f80,0x3f803f80,0x3f803f80,0x3f803f80,0x3f803f80,
  0x3f803f80,0x3f803f80,0x3f803f80,0x3f803f80,0x3f803f80,0x3f803f80,0x3f803f80,0x3f803f80,0x3f803f80,0x3f803f80,0x3f803f80,0x3f803f80,
  0x3f803f80,0x3f803f80,0x3f803f80,0x3f803f80,0x3f803f80,0x3f803f80,0x3f803f80,0x3f803f80,0x3f803f80,0x3f803f80,0x3f803f80,0x3f803f80,
  0x3f803f80,0x3f803f80,0x3f803f80,0x3f803f80,0x3f803f80,0x3f803f80,0x3f803f80,0x3f803f80,0x3f803f80,0x3f803f80,0x3f803f80,0x3f803f80,
  0x3f803f80,0x3f803f80,0x3f803f80,0x3f803f80,0x3f803f80,0x3f803f80,0x3f803f80,0x3f803f80,0x3f803f80,0x3f803f80,0x3f803f80,0x3f803f80,
  0x3f803f80,0x3f803f80,0x3f803f80,0x3f803f80,0x3f803f80,0x3f803f80,0x3f803f80,0x3f803f80,0x3f803f80,0x3f803f80,0x3f803f80,0x3f803f80,
  0x3f803f80,0x3f803f80,0x3f803f80,0x3f803f80,0x3f803f80,0x3f803f80,0x3f803f80,0x3f803f80,0x3f803f80,0x3f803f80,0x3f803f80,0x3f803f80,
  0x3f803f80,0x3f803f80,0x3f803f80,0x3f803f80,0x3f803f80,0x3f803f80,0x3f803f80,0x3f803f80,0x3f803f80,0x3f803f80,0x3f803f80,0x3f803f80,
  0x3f803f80,0x3f803f80,0x3f803f80,0x3f803f80,0x3f803f80,0x3f803f80,0x3f803f80,0x3f803f80,0x3f803f80,0x3f803f80,0x3f803f80,0x3f803f80,
  0x3f803f80,0x3f803f80,0x3f803f80,0x3f803f80,0x3f803f80,0x3f803f80,0x3f803f80,0x3f803f80,0x3f803f80,0x3f803f80,0x3f803f80,0x3f803f80,
  0x3f803f80,0x3f803f80,0x3f803f80,0x3f803f80,0x3f803f80,0x3f803f80,0x3f803f80,0x3f803f80,0x3f803f80,0x3f803f80,0x3f803f80,0x3f803f80,
  0x3f803f80,0x3f803f80,0x3f803f80,0x3f803f80,0x3f803f80,0x3f803f80,0x3f803f80,0x3f803f80,0x3f803f80,0x3f803f80,0x3f803f80,0x3f803f80,
  0x3f803f80,0x3f803f80,0x3f803f80,0x3f803f80,0x3f803f80,0x3f803f80,0x3f803f80,0x3f803f80,0x3f803f80,0x3f803f80,0x3f803f80,0x3f803f80,
  0x3f803f80,0x3f803f80,0x3f803f80,0x3f803f80,0x3f803f80,0x3f803f80,0x3f803f80,0x3f803f80,0x3f803f80,0x3f803f80,0x3f803f80,0x3f803f80,
  0x3f803f80,0x3f803f80,0x3f803f80,0x3f803f80,0x3f803f80,0x3f803f80,0x3f803f80,0x3f803f80,0x3f803f80,0x3f803f80,0x3f803f80,0x3f803f80,
  0x3f803f80,0x3f803f80,0x3f803f80,0x3f803f80,0x3f803f80,0x3f803f80,0x3f803f80,0x3f803f80,0x3f803f80,0x3f803f80,0x3f803f80,0x3f803f80,
  0x3f803f80,0x3f803f80,0x3f803f80,0x3f803f80,0x3f803f80,0x3f803f80,0x3f803f80,0x3f803f80,0x3f803f80,0x3f803f80,0x3f803f80,0x3f803f80,
  0x3f803f80,0x3f803f80,0x3f803f80,0x3f803f80,0x3f803f80,0x3f803f80,0x3f803f80,0x3f803f80,0x3f803f80,0x3f803f80,0x3f803f80,0x3f803f80,
  0x3f803f80,0x3f803f80,0x3f803f80,0x3f803f80,0x3f803f80,0x3f803f80,0x3f803f80,0x3f803f80,0x3f803f80,0x3f803f80,0x3f803f80,0x3f803f80,
  0x3f803f80,0x3f803f80,0x3f803f80,0x3f803f80,0x3f803f80,0x3f803f80,0x3f803f80,0x3f803f80,0x3f803f80,0x3f803f80,0x3f803f80,0x3f803f80,
  0x3f803f80,0x3f803f80,0x3f803f80,0x3f803f80,0x3f803f80,0x3f803f80,0x3f803f80,0x3f803f80,0x3f803f80,0x3f803f80,0x3f803f80,0x3f803f80,
  0x3f803f80,0x3f803f80,0x3f803f80,0x3f803f80,0x3f803f80,0x3f803f80,0x3f803f80,0x3f803f80,0x3f803f80,0x3f803f80,0x3f803f80,0x3f803f80,
  0x3f803f80,0x3f803f80,0x3f803f80,0x3f803f80,0x3f803f80,0x3f803f80,0x3f803f80,0x3f803f80,0x3f803f80,0x3f803f80,0x3f803f80,0x3f803f80,
  0x3f803f80,0x3f803f80,0x3f803f80,0x3f803f80,0x3f803f80,0x3f803f80,0x3f803f80,0x3f803f80,0x3f803f80,0x3f803f80,0x3f803f80,0x3f803f80,
  0x3f803f80,0x3f803f80,0x3f803f80,0x3f803f80,0x3f803f80,0x3f803f80,0x3f803f80,0x3f803f80,0x3f803f80,0x3f803f80,0x3f803f80,0x3f803f80,
  0x3f803f80,0x3f803f80,0x3f803f80,0x3f803f80,0x3f803f80,0x3f803f80,0x3f803f80,0x3f803f80,0x3f803f80,0x3f803f80,0x3f803f80,0x3f803f80,
  0x3f803f80,0x3f803f80,0x3f803f80,0x3f803f80,0x3f803f80,0x3f803f80,0x3f803f80,0x3f803f80,0x3f803f80,0x3f803f80,0x3f803f80,0x3f803f80,
  0x3f803f80,0x3f803f80,0x3f803f80,0x3f803f80,0x3f803f80,0x3f803f80,0x3f803f80,0x3f803f80,0x3f803f80,0x3f803f80,0x3f803f80,0x3f803f80,
  0x3f803f80,0x3f803f80,0x3f803f80,0x3f803f80,0x3f803f80,0x3f803f80,0x3f803f80,0x3f803f80,0x3f803f80,0x3f803f80,0x3f803f80,0x3f803f80,
  0x3f803f80,0x3f803f80,0x3f803f80,0x3f803f80,0x3f803f80,0x3f803f80,0x3f803f80,0x3f803f80,0x3f803f80,0x3f803f80,0x3f803f80,0x3f803f80,
  0x3f803f80,0x3f803f80,0x3f803f80,0x3f803f80,0x3f803f80,0x3f803f80,0x3f803f80,0x3f803f80,0x3f803f80,0x3f803f80,0x3f803f80,0x3f803f80,
  0x3f803f80,0x3f803f80,0x3f803f80,0x3f803f80,0x3f803f80,0x3f803f80,0x3f803f80,0x3f803f80,0x3f803f80,0x3f803f80,0x3f803f80,0x3f803f80,
  0x3f803f80,0x3f803f80,0x3f803f80,0x3f803f80,0x3f803f80,0x3f803f80,0x3f803f80,0x3f803f80,0x3f803f80,0x3f803f80,0x3f803f80,0x3f803f80,
  0x3f803f80,0x3f803f80,0x3f803f80,0x3f803f80,0x3f803f80,0x3f803f80,0x3f803f80,0x3f803f80,0x3f803f80,0x3f803f80,0x3f803f80,0x3f803f80,
  0x3f803f80,0x3f803f80,0x3f803f80,0x3f803f80,0x3f803f80,0x3f803f80,0x3f803f80,0x3f803f80,0x3f803f80,0x3f803f80,0x3f803f80,0x3f803f80,
  0x3f803f80,0x3f803f80,0x3f803f80,0x3f803f80,0x3f803f80,0x3f803f80,0x3f803f80,0x3f803f80,0x3f803f80,0x3f803f80,0x3f803f80,0x3f803f80,
  0x3f803f80,0x3f803f80,0x3f803f80,0x3f803f80,0x3f803f80,0x3f803f80,0x3f803f80,0x3f803f80,0x3f803f80,0x3f803f80,0x3f803f80,0x3f803f80,
  0x3f803f80,0x3f803f80,0x3f803f80,0x3f803f80,0x3f803f80,0x3f803f80,0x3f803f80,0x3f803f80,0x3f803f80,0x3f803f80,0x3f803f80,0x3f803f80,
  0x3f803f80,0x3f803f80,0x3f803f80,0x3f803f80,0x3f803f80,0x3f803f80,0x3f803f80,0x3f803f80,0x3f803f80,0x3f803f80,0x3f803f80,0x3f803f80,
  0x3f803f80,0x3f803f80,0x3f803f80,0x3f803f80,0x3f803f80,0x3f803f80,0x3f803f80,0x3f803f80,0x3f803f80,0x3f803f80,0x3f803f80,0x3f803f80,
  0x3f803f80,0x3f803f80,0x3f803f80,0x3f803f80,0x3f803f80,0x3f803f80,0x3f803f80,0x3f803f80,0x3f803f80,0x3f803f80,0x3f803f80,0x3f803f80,
  0x3f803f80,0x3f803f80,0x3f803f80,0x3f803f80,0x3f803f80,0x3f803f80,0x3f803f80,0x3f803f80,0x3f803f80,0x3f803f80,0x3f803f80,0x3f803f80,
  0x3f803f80,0x3f803f80,0x3f803f80,0x3f803f80,
};

__device__ __align__(128) float    g_part[16][8][2176];
__device__ __align__(128) float    g_kv[16][2176];
__device__ __align__(128) uint4    g_o[16 * 16 * 1024];
__device__ __align__(128) unsigned g_ocnt[2 * 16 * 32];
__device__ unsigned g_epoch[128];
#define GSTAMP(role, i) do {} while (0)
#define STAMP(role, i) do {} while (0)
#define PDUMP(role) do {} while (0)
#define PROF_SMEM 0

constexpr int STAGE_BYTES = 57344;
constexpr int OFF_H = 4 * 16384, OFF_VP = 9 * 16384, OFF_SPARE = 10 * 16384;
constexpr int OFF_XT = 172032, XT_STRIDE = 4112;
constexpr int OFF_BAR = 204928, OFF_EPOCH = OFF_BAR + 640, OFF_EX = OFF_BAR + 656, OFF_D = OFF_BAR + 672, OFF_SCALE = OFF_BAR + 704;
constexpr int OFF_F2F = 205824, OFF_F2I = 207872, OFF_F4 = 209920, OFF_ONES = 214016, OFF_KVB = 214016;
constexpr int OFF_STG = 219136, STG_STRIDE = 4352, SMEM_TOTAL = 232192 + PROF_SMEM;
enum { B_FULL1 = 0, B_EMPTY1 = 3, B_Q = 6, B_ODONE1 = 7, B_O1RDY = 8, B_H = 9, B_XRAW = 10, B_XT = 11, B_KV = 12, B_Y = 13,  B_AFREE = 15,
       B_STG = 18, B_ODONE = 24, B_XFREE = 25, B_FULL2 = 33, B_CONS2 = 49, B_SFREE = 14, B_PKRDY = 62, B_PKFREE = 64, B_H2 = 65, B_G1DONE = 66, B_COUNT = 67 };
constexpr uint64_t SLOT_A = 0x6859468594685948ull, SLOT_B = 0x7103271032710326ull;
constexpr int NPRE = 6, BEARLY = 3;
__host__ __device__ constexpr int bar_count(int i) {
  return i < B_EMPTY1 ? 1 : i < B_Q ? 4 : i == B_XT ? 4 : i == B_H ? 4 : (i == B_SFREE || i == B_G1DONE) ? 2 : i >= B_PKFREE ? 4 : i >= B_PKRDY ? 8 : i == B_KV ? 2 : i == B_Y ? 9
       : (i >= B_AFREE && i < B_STG) ? 16 : (i == B_ODONE || i == B_ODONE1) ? 8 : (i >= B_XFREE && i < B_FULL2) ? 4
       : i >= B_CONS2 ? 4 : (i >= B_FULL2 && i < B_FULL2 + NPRE) ? 2 : 1;
}
__host__ __device__ constexpr uint64_t bar_counts(int r) {
  uint64_t v = 0;
  for (int w = 0; w < 11; w++) v |= (uint64_t)(bar_count(1 + 11 * r + w) - 1) << (4 * w);
  return v;
}
constexpr uint32_t SW128 = 64 | (1u << 30);
constexpr int SPIN_LIMIT = 1 << 22;
#define PFD 3
#define PD1 700
#define PD2 450
#define QPF 6
#define BPACE 250
#define OCH 3
#define O1D 1
#define HOLD2 12
#define D1 200
#define TRICK 3
#define HSTART 1500
#define PACE 800

__device__ __forceinline__ uint32_t smem_u32(const void* p) { return (uint32_t)__cvta_generic_to_shared(p); }
__device__ __forceinline__ void wg_fence() { asm volatile("wgmma.fence.sync.aligned;" ::: "memory"); }
__device__ __forceinline__ void wg_commit() { asm volatile("wgmma.commit_group.sync.aligned;" ::: "memory"); }
template <int N> __device__ __forceinline__ void wg_wait() { asm volatile("wgmma.wait_group.sync.aligned %0;" ::"n"(N) : "memory"); }
template <int N> __device__ __forceinline__ void keep(float (&d)[N]) {
#pragma unroll
  for (int i = 0; i < N; i++) asm volatile("" : "+f"(d[i])::"memory");
}
__device__ __forceinline__ void mbar_init(uint32_t bar, int cnt) { asm volatile("mbarrier.init.shared::cta.b64 [%0], %1;" ::"r"(bar), "r"(cnt)); }
__device__ __forceinline__ void mbar_expect(uint32_t bar, int bytes) { asm volatile("mbarrier.arrive.expect_tx.shared::cta.b64 _, [%0], %1;" ::"r"(bar), "r"(bytes) : "memory"); }
__device__ __forceinline__ void mbar_arrive(uint32_t bar) { asm volatile("mbarrier.arrive.shared::cta.b64 _, [%0];" ::"r"(bar) : "memory"); }
__device__ __forceinline__ void mbar_arrive_cl(uint32_t bar, uint32_t cta) {
  asm volatile("{\n.reg .b32 r;\nmapa.shared::cluster.u32 r, %0, %1;\nmbarrier.arrive.shared::cluster.b64 _, [r];\n}\n" ::"r"(bar), "r"(cta) : "memory");
}
__device__ __forceinline__ void mbar_wait(uint32_t bar, uint32_t parity) {
  asm volatile("{\n.reg .pred p;\n.reg .u32 n;\nmov.u32 n, 0;\n"
               "W_%=:\nmbarrier.try_wait.parity.shared::cta.b64 p, [%0], %1;\n@p bra D_%=;\n"
               "add.u32 n, n, 1;\nsetp.lt.u32 p, n, %2;\n@p bra W_%=;\ntrap;\nD_%=:\n}\n" ::"r"(bar), "r"(parity), "n"(SPIN_LIMIT) : "memory");
}
__device__ __forceinline__ void fence_async() { asm volatile("fence.proxy.async.shared::cta;" ::: "memory"); }
__device__ __forceinline__ void bar_sync(int id) { asm volatile("bar.sync %0, 128;" ::"r"(id) : "memory"); }
__device__ __forceinline__ void tma2d(uint32_t dst, const CUtensorMap* m, int c0, int c1, uint32_t bar) {
  asm volatile("cp.async.bulk.tensor.2d.shared::cluster.global.mbarrier::complete_tx::bytes [%0], [%1, {%3, %4}], [%2];"
               ::"r"(dst), "l"(m), "r"(bar), "r"(c0), "r"(c1) : "memory");
}
__device__ __forceinline__ void tma2d_mc(uint32_t dst, const CUtensorMap* m, int c0, int c1, uint32_t bar) {
  asm volatile("cp.async.bulk.tensor.2d.shared::cluster.global.mbarrier::complete_tx::bytes.multicast::cluster [%0], [%1, {%3, %4}], [%2], %5;"
               ::"r"(dst), "l"(m), "r"(bar), "r"(c0), "r"(c1), "h"((uint16_t)3) : "memory");
}
__device__ __forceinline__ void tma3d(uint32_t dst, const CUtensorMap* m, int c0, int c1, int c2, uint32_t bar) {
  asm volatile("cp.async.bulk.tensor.3d.shared::cluster.global.mbarrier::complete_tx::bytes [%0], [%1, {%3, %4, %5}], [%2];"
               ::"r"(dst), "l"(m), "r"(bar), "r"(c0), "r"(c1), "r"(c2) : "memory");
}
__device__ __forceinline__ void tma4d(uint32_t dst, const CUtensorMap* m, int c0, int c1, int c2, int c3, uint32_t bar) {
  asm volatile("cp.async.bulk.tensor.4d.shared::cluster.global.mbarrier::complete_tx::bytes [%0], [%1, {%3, %4, %5, %6}], [%2];"
               ::"r"(dst), "l"(m), "r"(bar), "r"(c0), "r"(c1), "r"(c2), "r"(c3) : "memory");
}
__device__ __forceinline__ void bulk_ld(uint32_t dst, const void* src, int bytes, uint32_t bar) {
  asm volatile("cp.async.bulk.shared::cluster.global.mbarrier::complete_tx::bytes [%0], [%1], %2, [%3];" ::"r"(dst), "l"(src), "r"(bytes), "r"(bar) : "memory");
}
__device__ __forceinline__ void bulk_ld_mc(uint32_t dst, const void* src, int bytes, uint32_t bar) {
  asm volatile("cp.async.bulk.shared::cluster.global.mbarrier::complete_tx::bytes.multicast::cluster [%0], [%1], %2, [%3], %4;"
               ::"r"(dst), "l"(src), "r"(bytes), "r"(bar), "h"((uint16_t)3) : "memory");
}
__device__ __forceinline__ void tma2d_st(const CUtensorMap* m, uint32_t src, int c0, int c1) {
  asm volatile("cp.async.bulk.tensor.2d.global.shared::cta.bulk_group [%0, {%2, %3}], [%1];" ::"l"(m), "r"(src), "r"(c0), "r"(c1) : "memory");
}
__device__ __forceinline__ void ldsm4(uint32_t (&r)[4], uint32_t a) {
  asm volatile("ldmatrix.sync.aligned.m8n8.x4.shared.b16 {%0,%1,%2,%3}, [%4];" : "=r"(r[0]), "=r"(r[1]), "=r"(r[2]), "=r"(r[3]) : "r"(a) : "memory");
}
__device__ __forceinline__ void ldsm4t(uint32_t (&r)[4], uint32_t a) {
  asm volatile("ldmatrix.sync.aligned.m8n8.x4.trans.shared.b16 {%0,%1,%2,%3}, [%4];" : "=r"(r[0]), "=r"(r[1]), "=r"(r[2]), "=r"(r[3]) : "r"(a) : "memory");
}
__device__ __forceinline__ void stsm4(uint32_t a, uint32_t r0, uint32_t r1, uint32_t r2, uint32_t r3) {
  asm volatile("stmatrix.sync.aligned.m8n8.x4.shared.b16 [%0], {%1,%2,%3,%4};" ::"r"(a), "r"(r0), "r"(r1), "r"(r2), "r"(r3) : "memory");
}
__device__ __forceinline__ uint32_t pk2(float lo, float hi) { uint32_t r; asm("cvt.rn.bf16x2.f32 %0, %1, %2;" : "=r"(r) : "f"(hi), "f"(lo)); return r; }
__device__ __forceinline__ uint32_t hmul(uint32_t a, uint32_t b) { uint32_t r; asm("mul.rn.bf16x2 %0, %1, %2;" : "=r"(r) : "r"(a), "r"(b)); return r; }
__device__ __forceinline__ uint32_t hadd(uint32_t a, uint32_t b) { uint32_t r; asm("add.rn.bf16x2 %0, %1, %2;" : "=r"(r) : "r"(a), "r"(b)); return r; }
__device__ __forceinline__ uint32_t hmin(uint32_t a, uint32_t b) { uint32_t r; asm("min.bf16x2 %0, %1, %2;" : "=r"(r) : "r"(a), "r"(b)); return r; }
__device__ __forceinline__ uint32_t hmaxabs(uint32_t a, uint32_t b) { uint32_t r; asm("max.xorsign.abs.bf16x2 %0, %1, %2;" : "=r"(r) : "r"(a), "r"(b)); return r; }
__device__ __forceinline__ float ex2(float x) { float r; asm("ex2.approx.ftz.f32 %0, %1;" : "=f"(r) : "f"(x)); return r; }
__device__ __forceinline__ float rcp_fast(float x) { float r; asm("rcp.approx.ftz.f32 %0, %1;" : "=f"(r) : "f"(x)); return r; }
__device__ __forceinline__ uint32_t phi2(float lo, float hi) {
  uint32_t t;
  asm("cvt.rn.relu.bf16x2.f32 %0, %1, %2;" : "=r"(t) : "f"(hi), "f"(lo));
  const uint32_t e = pk2(ex2(lo * 1.4426950408889634f), ex2(hi * 1.4426950408889634f));
  return hadd(hadd(t, hmin(e, 0x3F803F80u)), 0x35863586u);
}
__device__ __forceinline__ bool opaque_true() { uint32_t v; asm volatile("mov.u32 %0, %%nctaid.y;" : "=r"(v)); return v != 0; }
__device__ __forceinline__ int norm_exp(uint32_t (&v)[32], float f0) {
  uint32_t m[4] = {hmaxabs(__float_as_uint(f0) >> 16, v[0]), v[1], v[2], v[3]};
#pragma unroll
  for (int i = 4; i < 32; i++) m[i & 3] = hmaxabs(m[i & 3], v[i]);
  m[0] = hmaxabs(hmaxabs(m[0], m[1]), hmaxabs(m[2], m[3]));
  const int e = min(max((int)(__reduce_max_sync(~0u, max(m[0] & 0x7FFFu, (m[0] >> 16) & 0x7FFFu)) >> 7), 1), 253);
  if (e > 141) {
#pragma unroll
    for (int i = 0; i < 32; i++) v[i] = hmul(v[i], 0x07000700u);
  }
  return e;
}
__device__ __forceinline__ void norm_cvt(uint32_t (&v)[32], float f0, int e) {
  const uint32_t sc = (e > 141 ? 255 - e : 142 - e) * 0x00800080u;
#pragma unroll
  for (int i = 0; i < 32; i++) {
    const uint32_t a = hmul(v[i], sc);
    v[i] = (a & 0x0FFF0FFFu) * 7 + a;
  }
  v[0] = __byte_perm(v[0], __half_as_ushort(__float2half_rn(f0 * __uint_as_float((254 - e) << 23))), 0x3254);
}
__device__ __forceinline__ void poll_ge(const unsigned* p, unsigned target) {
#pragma unroll 1
  for (int n = 0; n < SPIN_LIMIT; n++) {
    unsigned v;
    asm volatile("ld.relaxed.gpu.global.u32 %0, [%1];" : "=r"(v) : "l"(p) : "memory");
    if (__all_sync(~0u, (int)(v - target) >= 0)) { asm volatile("fence.acquire.gpu;" ::: "memory"); return; }
  }
  __trap();
}

__device__ __forceinline__ bool elect_one() {
  uint32_t p;
  asm volatile("{\n.reg .pred p;\nelect.sync _|p, 0xffffffff;\nselp.u32 %0, 1, 0, p;\n}\n" : "=r"(p));
  return p;
}
__device__ __forceinline__ uint4 ld_na4(const void* p) {
  uint4 v;
  asm volatile("ld.global.L1::no_allocate.v4.u32 {%0,%1,%2,%3}, [%4];" : "=r"(v.x), "=r"(v.y), "=r"(v.z), "=r"(v.w) : "l"(p) : "memory");
  return v;
}
__device__ __forceinline__ void st_cg4(void* p, uint4 v) {
  asm volatile("st.global.cg.v4.u32 [%0], {%1,%2,%3,%4};" ::"l"(p), "r"(v.x), "r"(v.y), "r"(v.z), "r"(v.w) : "memory");
}
__device__ __forceinline__ uint32_t mapa(uint32_t a, uint32_t cta) { uint32_t r; asm("mapa.shared::cluster.u32 %0, %1, %2;" : "=r"(r) : "r"(a), "r"(cta)); return r; }
__device__ __forceinline__ void st_async(uint32_t a, uint32_t v, uint32_t bar) {
  asm volatile("st.async.weak.shared::cluster.mbarrier::complete_tx::bytes.b32 [%0], %1, [%2];" ::"r"(a), "r"(v), "r"(bar) : "memory");
}
__device__ __forceinline__ void st_async4(uint32_t a, uint32_t x, uint32_t y, uint32_t z, uint32_t w, uint32_t bar) {
  asm volatile("st.async.weak.shared::cluster.mbarrier::complete_tx::bytes.v4.b32 [%0], {%1,%2,%3,%4}, [%5];" ::"r"(a), "r"(x), "r"(y), "r"(z), "r"(w), "r"(bar) : "memory");
}
__device__ __forceinline__ void tma3d_st(const CUtensorMap* m, uint32_t src, int c0, int c1, int c2) {
  asm volatile("cp.async.bulk.tensor.3d.global.shared::cta.bulk_group [%0, {%2, %3, %4}], [%1];" ::"l"(m), "r"(src), "r"(c0), "r"(c1), "r"(c2) : "memory");
}
__device__ __forceinline__ uint4 ld_rlx4(const void* p) {
  uint4 v;
  asm volatile("{\n.reg .b128 t;\n.reg .b64 a, b;\nld.relaxed.gpu.global.b128 t, [%4];\nmov.b128 {a, b}, t;\nmov.b64 {%0, %1}, a;\nmov.b64 {%2, %3}, b;\n}\n"
               : "=r"(v.x), "=r"(v.y), "=r"(v.z), "=r"(v.w) : "l"(p) : "memory");
  return v;
}
__device__ __forceinline__ void ld_stale4(uint4& v, const void* p, uint32_t tag) {
  asm volatile("{\n.reg .b128 t;\n.reg .b64 a, b;\n.reg .b32 x;\n.reg .pred p;\n"
               "lop3.b32 x, %0, %5, 1, 0x28;\nsetp.ne.u32 p, x, 0;\n"
               "mov.b64 a, {%0, %1};\nmov.b64 b, {%2, %3};\nmov.b128 t, {a, b};\n"
               "@p ld.relaxed.gpu.global.b128 t, [%4];\n"
               "mov.b128 {a, b}, t;\nmov.b64 {%0, %1}, a;\nmov.b64 {%2, %3}, b;\n}\n"
               : "+r"(v.x), "+r"(v.y), "+r"(v.z), "+r"(v.w) : "l"(p), "r"(tag) : "memory");
}
__device__ __forceinline__ void st_tag4(void* p, float a, float b, float c, float d, uint32_t tag) {
  asm volatile("{\n.reg .b128 t;\n.reg .b64 a, b;\nmov.b64 a, {%1, %2};\nmov.b64 b, {%3, %4};\nmov.b128 t, {a, b};\nst.relaxed.gpu.global.b128 [%0], t;\n}\n"
               ::"l"(p), "r"((__float_as_uint(a) & ~1u) | tag), "f"(b), "f"(c), "f"(d) : "memory");
}
__device__ __forceinline__ uint32_t stale8(const uint4 (&f)[8], uint32_t tag) {
  uint32_t r[4];
#pragma unroll
  for (int i = 0; i < 4; i++) asm("lop3.b32 %0, %1, %2, %3, 0x7E;" : "=r"(r[i]) : "r"(f[2 * i].x), "r"(f[2 * i + 1].x), "r"(tag));
  asm("lop3.b32 %0, %0, %1, %2, 0xFE;" : "+r"(r[0]) : "r"(r[1]), "r"(r[2]));
  return r[0] | r[3];
}

struct ConvC { uint32_t a1[2][4], wa[2], wb[2], sg; };
__device__ __forceinline__ uint64_t dsc(uint32_t lo, uint32_t hi) { return ((uint64_t)hi << 32) | lo; }
__device__ __forceinline__ uint32_t hfma(uint32_t a, uint32_t b, uint32_t c) { uint32_t r; asm("fma.rn.f16x2 %0, %1, %2, %3;" : "=r"(r) : "r"(a), "r"(b), "r"(c)); return r; }
__device__ __forceinline__ uint32_t hfnma(uint32_t a, uint32_t b, uint32_t c) { uint32_t r; asm("{.reg .b32 n; neg.f16x2 n, %1; fma.rn.f16x2 %0, n, %2, %3;}" : "=r"(r) : "r"(a), "r"(b), "r"(c)); return r; }
__device__ __forceinline__ uint32_t hmul16(uint32_t a, uint32_t b) { uint32_t r; asm("mul.rn.f16x2 %0, %1, %2;" : "=r"(r) : "r"(a), "r"(b)); return r; }
template <int N> __device__ __forceinline__ void keepu(uint32_t (&d)[N]) {
#pragma unroll
  for (int i = 0; i < N; i++) asm volatile("" : "+r"(d[i])::"memory");
}
__device__ __forceinline__ void conv_m1(const ConvC& K, uint32_t (&u)[16], uint32_t l) {
  wg_fence();
  wgmma_hrs_n64<1>(u, K.a1[0][0], K.a1[0][1], K.a1[0][2], K.a1[0][3], dsc(l, 32), 0);
  wgmma_hrs_n64<1>(u, K.a1[1][0], K.a1[1][1], K.a1[1][2], K.a1[1][3], dsc(l + 16, 32), 1);
  wg_commit();
}
__device__ __forceinline__ void conv_s2(const ConvC& K, uint32_t (&u)[16], uint32_t (&Z)[2][8], uint32_t dfl) {
  uint32_t fr[8], fi[8];
#pragma unroll
  for (int c = 0; c < 8; c++) {
    const uint32_t r = hfma(K.wa[c & 1], u[2 * c + 1], u[2 * c]);
    fi[c] = hfma(K.wb[c & 1], r, u[2 * c + 1]);
    fr[c] = hfma(K.wa[c & 1], fi[c], r);
  }
  wg_fence();
#pragma unroll
  for (int p = 0; p < 2; p++) {
    wgmma_hrs_n32<0>(Z[p], fr[4 * p], fr[4 * p + 2], fr[4 * p + 1], fr[4 * p + 3], dsc(dfl, 32), 0);
    wgmma_hrs_n32<0>(Z[p], fi[4 * p], fi[4 * p + 2], fi[4 * p + 1], fi[4 * p + 3], dsc(dfl + 16, 32), 1);
  }
  wg_commit();
}
__device__ __forceinline__ void conv_win(const ConvC& K, const uint32_t (&X)[2][8], uint32_t (&W)[2][8]) {
#pragma unroll
  for (int b = 0; b < 4; b++)
#pragma unroll
    for (int c = 0; c < 2; c++) {
      const uint32_t xr = X[b >> 1][2 * c + (b & 1)], xi = X[b >> 1][4 + 2 * c + (b & 1)];
      const int a = b ? b - 1 : 0;
      W[b >> 1][2 * c + (b & 1)] = b ? hfnma(K.sg, X[a >> 1][4 + 2 * c + (a & 1)], xr) : hmul16(xr, 0x3C003C00u);
      W[b >> 1][4 + 2 * c + (b & 1)] = b ? hfma(K.sg, X[a >> 1][2 * c + (a & 1)], xi) : hmul16(xi, 0x3C003C00u);
    }
}
template <int p>
__device__ __forceinline__ void conv_pw(uint32_t (&X)[2][8], uint32_t (&H)[2][8], uint32_t (&V)[8], uint32_t dil) {
  uint32_t pr[2][2], pi[2][2];
#pragma unroll
  for (int jj = 0; jj < 2; jj++)
#pragma unroll
    for (int c = 0; c < 2; c++) {
      const int j = 2 * p + jj;
      uint32_t sr = 0, si = 0;
#pragma unroll
      for (int a = 0; a <= j; a++) {
        const int b = j - a;
        const uint32_t hr = H[a >> 1][2 * c + (a & 1)], hi = H[a >> 1][4 + 2 * c + (a & 1)];
        const uint32_t xr = X[b >> 1][2 * c + (b & 1)], xi = X[b >> 1][4 + 2 * c + (b & 1)];
        sr = a == 0 ? hmul16(hr, xr) : hfma(hr, xr, sr);
        si = a == 0 ? hmul16(hr, xi) : hfma(hr, xi, si);
        sr = hfnma(hi, xi, sr);
        si = hfma(hi, xr, si);
      }
      pr[jj][c] = sr; pi[jj][c] = si;
    }
  wg_fence();
  wgmma_hrs_n32<0>(V, pr[0][0], pr[1][0], pr[0][1], pr[1][1], dsc(dil, 32), 0);
  wgmma_hrs_n32<0>(V, pi[0][0], pi[1][0], pi[0][1], pi[1][1], dsc(dil + 16, 32), 1);
  wg_commit();
}
template <int p>
__device__ __forceinline__ void conv_it(const ConvC& K, uint32_t (&V)[8], uint32_t vst) {
#pragma unroll
  for (int jj = 0; jj < 2; jj++) {
    uint32_t wr[2], wi[2];
#pragma unroll
    for (int c = 0; c < 2; c++) {
      const uint32_t r = hfnma(K.wa[c], V[4 + 2 * c + jj], V[2 * c + jj]);
      wi[c] = hfnma(K.wb[c], r, V[4 + 2 * c + jj]);
      wr[c] = hfnma(K.wa[c], wi[c], r);
    }
    stsm4(vst + (2 * p + jj) * 2048, wr[0], wr[1], wi[0], wi[1]);
  }
}
__device__ __forceinline__ void conv_m4(uint32_t (&y)[8], uint32_t (&a)[4][4], uint32_t d4l) {
  wg_fence();
  wgmma_hrs_n32<0>(y, a[0][0], a[0][1], a[0][2], a[0][3], dsc(d4l, 64), 0);
#pragma unroll
  for (int s = 1; s < 4; s++) wgmma_hrs_n32<0>(y, a[s][0], a[s][1], a[s][2], a[s][3], dsc(d4l + s * 16, 64), 1);
  wg_commit();
}

struct Params {
  CUtensorMap tmX, tmW, tmWo, tmWo1, tmK, tmV, tmQ, tmOA, tmOB;
  const __nv_bfloat16 *shift_k, *h, *D, *x, *w, *wo, *q;
  float *part, *kv;
  uint4* o;
  unsigned *ocnt, *epoch;
  const uint32_t *thr, *img;
};

__global__ void __cluster_dims__(2, 1, 1) __launch_bounds__(384, 1) fused_kernel(const __grid_constant__ Params P) {
  extern __shared__ __align__(1024) uint8_t smem[];
  const uint32_t sb = __shfl_sync(~0u, smem_u32(smem), 0);
  const uint32_t bars = sb + OFF_BAR;
  const int tid = threadIdx.x, lane = tid & 31;
  const int warp = __shfl_sync(~0u, tid >> 5, 0);
  const int rank = blockIdx.x & 1, cl = blockIdx.x >> 1;
  const unsigned c7 = cl + 6, g7 = (c7 * 37) >> 8;
  const int mb = cl < 4 ? 4 + cl : cl < 36 ? (cl - 4) >> 3 : g7 - 2;
  const int hq = cl < 4 ? 0 : cl < 36 ? (cl - 4) & 7 : 1 + c7 - 7 * g7;
  const int hp = 2 * hq + rank;
  const int rb = 2 * mb + (hq >> 2), cb = hq & 3;
#define BAR(i) (bars + 8 * (i))

  if (tid == 0) { STAMP(0, 0); GSTAMP(0, 30); }
  if (warp == 8) {
    if (elect_one()) {
      mbar_init(BAR(B_FULL1), 1);
      asm volatile("fence.mbarrier_init.release.cluster;" ::: "memory");
      mbar_expect(BAR(B_FULL1), STAGE_BYTES);
      tma2d(sb, &P.tmX, 0, mb * 256, BAR(B_FULL1));
      tma2d(sb + 16384, &P.tmX, 0, mb * 256 + 128, BAR(B_FULL1));
      tma3d(sb + 32768, &P.tmW, hp * 64, 0, 0, BAR(B_FULL1));
    }
    if (lane == 0) STAMP(3, 21);
  } else if (lane == 0) {
    const int wi = warp - (warp > 8);
#pragma unroll
    for (int r = 0; r < 6; r++)
      if (r < 5 || wi < B_COUNT - 56) mbar_init(BAR(1 + 11 * r + wi), ((uint32_t)(bar_counts(r) >> (4 * wi)) & 15) + 1);
    asm volatile("fence.mbarrier_init.release.cluster;" ::: "memory");
  }
  if (tid == 0) STAMP(2, 6);
  asm volatile("barrier.cluster.arrive.relaxed.aligned;\nbarrier.cluster.wait.aligned;" ::: "memory");
  if (tid == 256) STAMP(2, 7);

  if (warp < 8) {
    asm volatile("setmaxnreg.inc.sync.aligned.u32 224;");
    const int wg = warp >> 2, w = warp & 3, g = lane >> 2, q = lane & 3, t = tid & 127;
    const bool elect = (t == 0);
    const uint32_t s16 = (sb & 0x3FFFF) >> 4;
    uint32_t pq[2][16], ux[16], uh[16], X[4][2][8], H[4][2][8];
    ConvC K;
    const uint32_t dfl = s16 + (OFF_F2F >> 4) + (8 << 16), dil = s16 + (OFF_F2I >> 4) + (8 << 16), d4l = s16 + (OFF_F4 >> 4) + (8 << 16);
    const uint32_t xl = s16 + (OFF_XT >> 4) + 4 * wg * (XT_STRIDE >> 4) + (8 << 16);
    const uint32_t hl = s16 + (OFF_H >> 4) + wg * 512 + (8 << 16);
    {
      float acc[2][96];
      int st = 0, ph = 0;
#pragma unroll 1
      for (int kb = 0; kb < 14; kb++) {
        mbar_wait(BAR(B_FULL1 + st), ph);
        if (kb == 0 && elect) { STAMP(wg, 1); GSTAMP(wg, 26); }
        if (kb == 8 && elect) { STAMP(wg, 16); GSTAMP(wg, 25); }
        const uint32_t da = s16 + st * (STAGE_BYTES >> 4) + wg * 1024 + (1 << 16);
        const uint32_t db = s16 + st * (STAGE_BYTES >> 4) + 2048 + (512 << 16);
        wg_fence();
#pragma unroll
        for (int ks = 0; ks < 4; ks++) {
          wgmma_ss_n192<0, 1>(acc[0], dsc(da + ks * 2, SW128), dsc(db + ks * 128, SW128), (kb | ks) != 0);
          wgmma_ss_n192<0, 1>(acc[1], dsc(da + 512 + ks * 2, SW128), dsc(db + ks * 128, SW128), (kb | ks) != 0);
        }
        wg_commit();
        wg_wait<1>();
        if (kb > 0 && t < 2) mbar_arrive_cl(BAR(B_EMPTY1 + (st == 0 ? 2 : st - 1)), t);
        if (++st == 3) { st = 0; ph ^= 1; }
      }
#define TAIL_MMA(mt, stage) do { wg_fence(); _Pragma("unroll") for (int ks = 0; ks < 4; ks++) \
        wgmma_ss_n192<0, 1>(acc[mt], dsc(s16 + (stage) * (STAGE_BYTES >> 4) + wg * 1024 + (mt) * 512 + (1 << 16) + ks * 2, SW128), \
                            dsc(s16 + (stage) * (STAGE_BYTES >> 4) + 2048 + (512 << 16) + ks * 128, SW128), 1); wg_commit(); } while (0)
      mbar_wait(BAR(B_FULL1 + 2), 0);
      TAIL_MMA(0, 2);
      wg_wait<1>();
      if (elect) mbar_arrive(BAR(B_SFREE));
      mbar_wait(BAR(B_FULL1 + 0), 1);
      TAIL_MMA(0, 0);
      TAIL_MMA(1, 2);
      const uint32_t lrow = sb + wg * 16384 + (16 * w + 8 * ((lane >> 3) & 1) + (lane & 7)) * 128 + (((lane >> 4) ^ (lane & 7)) << 4);
#define E1K(mt, i) do { if (opaque_true()) { _Pragma("unroll") for (int j = (i); j < (i) + 2; j++) { \
          const float* a = &acc[mt][32 + 8 * j]; const float* b = a + 32; const uint32_t o = (lrow ^ (j * 32)) + (mt) * 8192; \
          stsm4(o + 2 * STAGE_BYTES, pk2(b[0], b[1]), pk2(b[2], b[3]), pk2(b[4], b[5]), pk2(b[6], b[7])); \
          stsm4(o, phi2(a[0], a[1]), phi2(a[2], a[3]), phi2(a[4], a[5]), phi2(a[6], a[7])); } } } while (0)
#define E1Q(mt) do { if (opaque_true()) { _Pragma("unroll") for (int i = 0; i < 16; i++) pq[mt][i] = phi2(acc[mt][2 * i], acc[mt][2 * i + 1]); } } while (0)
#define LOAD_K() do { const uint4* ct = (const uint4*)P.thr + t; \
        _Pragma("unroll") for (int s = 0; s < 2; s++) { const uint4 u = ld_na4(ct + s * 128); K.a1[s][0] = u.x; K.a1[s][1] = u.y; K.a1[s][2] = u.z; K.a1[s][3] = u.w; } \
        const uint4 u = ld_na4(ct + 2 * 128); K.wa[0] = u.x; K.wa[1] = u.y; K.wb[0] = u.z; K.wb[1] = u.w; \
        K.sg = (lane & 4) ? 0xBC00BC00u : 0x3C003C00u; } while (0)
#define PK_READY(mt) do { fence_async(); __syncwarp(); if (lane == 0) mbar_arrive(BAR(B_PKRDY + (mt))); } while (0)
      wg_wait<1>();
      keep(acc[0]);
      if (elect) STAMP(wg, 18);
      E1K(0, 0);
      TAIL_MMA(1, 0);
      E1K(0, 2);
      if (elect) STAMP(wg, 19);
      PK_READY(0);
      wg_wait<0>();
      keep(acc[1]);
      if (elect) mbar_arrive(BAR(B_G1DONE));
      asm volatile("setmaxnreg.dec.sync.aligned.u32 200;");
      if (elect) { STAMP(wg, 2); GSTAMP(wg, 27); }
      E1K(1, 0);
      if (elect) STAMP(wg, 20);
      E1K(1, 2);
      if (elect) STAMP(wg, 21);
      PK_READY(1);
      if (elect) STAMP(wg, 3);
      LOAD_K();
      if (elect) STAMP(wg, 4);
      E1Q(0);
      E1Q(1);
      if (elect) STAMP(wg, 17);
      mbar_wait(BAR(B_H), 0);
      conv_m1(K, ux, xl);
      conv_m1(K, uh, hl);
      wg_wait<1>(); keepu(ux);
      if (lane == 0) mbar_arrive_cl(BAR(B_XFREE + 4 * wg), rank ^ 1);
      conv_s2(K, ux, X[0], dfl);
      wg_wait<1>(); keepu(uh);
      conv_s2(K, uh, H[0], dfl);
    }
    if (elect) STAMP(wg, 5);
    {
      uint32_t vst = sb + wg * 8192 + w * 512 + lane * 16, vld = sb + wg * 8192 + w * 2048 + lane * 16;
      uint32_t ya = mapa(sb + OFF_XT + 4 * wg * XT_STRIDE + (2 * rank + (w & 1)) * 1024 + lane * 16, w >> 1);
      const uint32_t ybar = mapa(BAR(B_Y), w >> 1);
      asm volatile("" : "+r"(vst), "+r"(vld), "+r"(ya));
      uint32_t W[2][8], V0[8], V1[8], y[8], a[4][4];
      uint4 ov[4];
      uint4* const ot = P.o + ((2 * mb + wg) * 16 + hq) * 1024 + (16 * w + g) * 8 + ((4 * rank + q) ^ g);
#define YOUT(i) do { if ((w >> 1) == rank) { \
          asm volatile("st.shared.v4.b32 [%0], {%1,%2,%3,%4};" ::"r"(ya + (i) * XT_STRIDE), "r"(y[0]), "r"(y[2]), "r"(y[4]), "r"(y[6]) : "memory"); \
          asm volatile("st.shared.v4.b32 [%0], {%1,%2,%3,%4};" ::"r"(ya + (i) * XT_STRIDE + 512), "r"(y[1]), "r"(y[3]), "r"(y[5]), "r"(y[7]) : "memory"); \
        } else { \
          mbar_wait(BAR(B_XFREE + 4 * wg + (i)), 0); \
          st_async4(ya + (i) * XT_STRIDE, y[0], y[2], y[4], y[6], ybar); \
          st_async4(ya + (i) * XT_STRIDE + 512, y[1], y[3], y[5], y[7], ybar); } } while (0)
      auto ocalc = [&](const int hh) {
        if (hh == 0) {
          if (elect) STAMP(wg, 8);
          mbar_wait(BAR(B_KV), 0);
          if (elect) STAMP(wg, 9);
        }
        float oa[2][20];
        wg_fence();
#pragma unroll
        for (int m = 0; m < 4; m++) {
          const uint32_t* p = &pq[m & 1][8 * hh + 4 * (m >> 1)];
          wgmma_rs_n40<1>(oa[m & 1], p[0], p[1], p[2], p[3], dsc(s16 + (OFF_KVB >> 4) + hh * 160 + (m >> 1) * 16 + (8 << 16), 32), m >> 1);
        }
        wg_commit();
        wg_wait<0>();
#pragma unroll
        for (int mt = 0; mt < 2; mt++) {
          float (&o)[20] = oa[mt];
          keep(o);
          const uint32_t den = hadd(pk2(o[16], o[18]), 0x35863586u);
#pragma unroll
          for (int r = 0; r < 2; r++) {
            const float ri = rcp_fast(__uint_as_float(r ? (den & 0xFFFF0000u) : (den << 16)));
            uint4 u;
            u.x = pk2(o[2 * r] * ri, o[2 * r + 1] * ri);
            u.y = pk2(o[4 + 2 * r] * ri, o[5 + 2 * r] * ri);
            u.z = pk2(o[8 + 2 * r] * ri, o[9 + 2 * r] * ri);
            u.w = pk2(o[12 + 2 * r] * ri, o[13 + 2 * r] * ri);
            if (hh == 0) st_cg4(ot + (64 * mt + 8 * r) * 8, u); else ov[2 * mt + r] = u;
          }
        }
        if (hh == 0) {
          __syncwarp();
          if (lane == 0) mbar_arrive(BAR(B_ODONE));
          if (elect) STAMP(wg, 10);
        }
      };
      auto trickle = [&](const int qs) {
        const int m = qs - 2 * (OCH + O1D) - (TRICK - 1);
        if (m >= 0 && m < 4) {
          st_cg4(ot + 8 * 1024 + (64 * (m >> 1) + 8 * (m & 1)) * 8, ov[m]);
          if (m == 3) { __syncwarp(); if (lane == 0) mbar_arrive(BAR(B_ODONE1)); }
        }
      };
#pragma unroll
      for (int i = 0; i < 4; i++) {
        const bool nx = i < 3;
        const int n = nx ? i + 1 : i;
        const uint32_t vo = (i & 1) ? OFF_H + (i >> 1) * 16384 : OFF_VP;
        if (2 * i == OCH) ocalc(0);
        if (2 * i == OCH + O1D) ocalc(1);
        if (nx) {
          conv_m1(K, ux, xl + n * (XT_STRIDE >> 4));
          conv_m1(K, uh, hl + (n >> 1) * 1024 + (n & 1) * 256);
        }
        if (2 * i != OCH && 2 * i != OCH + O1D) { if (nx) { if (i > 0) wg_wait<3>(); else wg_wait<2>(); } else wg_wait<1>(); }
        keepu(X[i][0]); keepu(X[i][1]); keepu(H[i][0]); keepu(H[i][1]);
        conv_win(K, X[i], W);
        trickle(4 * i);
        conv_pw<0>(W, H[i], V0, dil);
        conv_pw<1>(W, H[i], V1, dil);
        trickle(4 * i + 1);
        wg_wait<2>();
        if (i > 0) { keepu(y); YOUT(i - 1); }
        if (2 * i + 1 == OCH) ocalc(0);
        if (2 * i + 1 == OCH + O1D) ocalc(1);
        if (nx) {
          keepu(ux); keepu(uh);
          if (lane == 0) mbar_arrive_cl(BAR(B_XFREE + 4 * wg + n), rank ^ 1);
          conv_s2(K, ux, X[n], dfl);
          wg_wait<1>();
        } else wg_wait<0>();
        keepu(V0); keepu(V1);
        trickle(4 * i + 2);
        if (i == 0) mbar_wait(BAR(B_H2), 0);
        conv_it<0>(K, V0, vst + vo);
        conv_it<1>(K, V1, vst + vo);
        bar_sync(1 + wg);
#pragma unroll
        for (int s = 0; s < 4; s++) ldsm4t(a[s], vld + vo + s * 512);
        if (nx) conv_s2(K, uh, H[n], dfl);
        conv_m4(y, a, d4l);
        trickle(4 * i + 3);
        if (i > 0 && lane < 2) mbar_arrive_cl(BAR(B_AFREE + i - 1), lane);
        if (elect && i < 3) STAMP(wg, i < 2 ? 6 + i : 9 + i);
      }
      wg_wait<0>(); keepu(y);
      YOUT(3);
      __syncwarp();
      if (lane == 0) mbar_arrive(BAR(B_Y));
      if (elect) STAMP(wg, 12);
    }
    {
      float acc[64];
#define G2_MMA(da, db, first) do { wg_fence(); _Pragma("unroll") for (int ks = 0; ks < 4; ks++) \
        wgmma_ss_n128<0, 1>(acc, dsc((da) + ks * 2, SW128), dsc((db) + ks * 128, SW128), ks || !(first)); wg_commit(); } while (0)
      const uint32_t a0 = s16 + wg * 512 + (1 << 16), b0 = s16 + (512 << 16);
      uint64_t ta = SLOT_A, tb = SLOT_B;
      uint32_t da = a0 + (SLOT_A & 15) * 1024, db = b0 + (SLOT_B & 15) * 1024, fb = BAR(B_FULL2);
      uint32_t cons = mapa(BAR(B_CONS2 - 1), t & 1);
      const bool rel = __shfl_sync(~0u, t, lane) < 2;
#pragma unroll 1
      for (int kb = 0; kb < HOLD2; kb++) {
        mbar_wait(fb, 0);
        if (kb == 0 && elect) { STAMP(wg, 13); GSTAMP(wg, 28); }
        G2_MMA(da, db, kb == 0);
        ta >>= 4; tb >>= 4;
        da = a0 + ((uint32_t)ta & 15) * 1024; db = b0 + ((uint32_t)tb & 15) * 1024; fb += 8;
        asm volatile("" : "+r"(da), "+r"(db));
        wg_wait<1>();
        if (kb > 0 && kb < 12 && rel) asm volatile("mbarrier.arrive.shared::cluster.b64 _, [%0];" ::"r"(cons) : "memory");
        cons += 8;
      }
#pragma unroll
      for (int kb = HOLD2; kb < 16; kb++) {
        if (wg == 1) mbar_wait(BAR(B_FULL2 + kb), 0);
        else if (kb == HOLD2) asm volatile("bar.sync 3, 256;" ::: "memory");
        G2_MMA(a0 + ((SLOT_A >> (4 * kb)) & 15) * 1024, b0 + ((SLOT_B >> (4 * kb)) & 15) * 1024, false);
      }
      if (wg == 1) asm volatile("bar.arrive 3, 256;" ::: "memory");
      const uint32_t stg = sb + wg * 8192 + w * 2048, so0 = ((SLOT_A >> 56) & 15) * 16384, so1 = ((SLOT_A >> 60) & 15) * 16384;
      const uint32_t lrow = stg + (8 * ((lane >> 3) & 1) + (lane & 7)) * 128 + (((lane >> 4) ^ (lane & 7)) << 4);
      const int col = 1024 + 256 * cb + 128 * rank, row = 128 * rb + 64 * wg + 16 * w;
      wg_wait<0>();
      keep(acc);
      if (elect) { STAMP(wg, 14); GSTAMP(wg, 29); }
#pragma unroll
      for (int cp = 0; cp < 8; cp++) {
        const float* a = &acc[8 * cp];
        stsm4((lrow ^ ((cp & 3) * 32)) + (cp >> 2 ? so1 : so0), pk2(a[0], a[1]), pk2(a[2], a[3]), pk2(a[4], a[5]), pk2(a[6], a[7]));
        if ((cp & 3) == 3) {
          fence_async();
          __syncwarp();
          if (elect_one()) tma2d_st(&P.tmOB, stg + (cp >> 2 ? so1 : so0), col + (cp >> 2) * 64, row);
        }
      }
      asm volatile("cp.async.bulk.commit_group;\ncp.async.bulk.wait_group.read 0;" ::: "memory");
      if (elect) {
        STAMP(wg, 15); GSTAMP(wg, 31); PDUMP(wg); if (wg == 0) PDUMP(2);
      }
    }
  } else {
    asm volatile("setmaxnreg.dec.sync.aligned.u32 56;");
    const int hw = warp - 9, g = lane >> 2, q = lane & 3;
#define sbar (bars + 8 * (B_STG - 18) + 16 * warp)
    if (warp == 8) {
      if (D1) __nanosleep(D1);
      int st = 1, pp = 1;
      const uint8_t* pfx = (const uint8_t*)P.x + (mb * 256 + hp * 16 + (lane & 15)) * 2048;
      const uint8_t* pfw = (const uint8_t*)P.w + (mb * 8 + (lane & 7)) * 6144 + (lane >> 3) * 2048 + hp * 128;
#pragma unroll 1
      for (int kb = 1; kb < 16; kb++) {
        if (kb >= 3) mbar_wait(BAR(B_EMPTY1 + st), pp);
        const uint32_t sa = sb + st * STAGE_BYTES;
        if (elect_one()) {
          mbar_expect(BAR(B_FULL1 + st), STAGE_BYTES);
          tma2d_mc(sa + rank * 16384, &P.tmX, kb * 64, mb * 256 + rank * 128, BAR(B_FULL1 + st));
          tma3d(sa + 32768, &P.tmW, hp * 64, kb * 64, 0, BAR(B_FULL1 + st));
        }
        if (kb == 1 && lane == 0) STAMP(2, 24);
        if (PFD && kb >= 2) {
#pragma unroll 1
          for (int j = kb == 2 ? 3 : kb + PFD; j <= kb + PFD && j < 16; j++) {
            if (lane < 16) asm volatile("prefetch.global.L2 [%0];" ::"l"(pfx + j * 128));
            if (lane < 24) asm volatile("prefetch.global.L2 [%0];" ::"l"(pfw + j * (64 * 6144)));
          }
          if (kb >= QPF && kb < QPF + 8) asm volatile("prefetch.global.L2 [%0];" ::"l"((const uint8_t*)P.q + (blockIdx.x * 256 + (kb - QPF) * 32 + lane) * 128));
          if (kb >= 4)
            asm volatile("prefetch.global.L2 [%0];" ::"l"(kb < 12 ? (const uint8_t*)P.h + ((2 * cl + rank) * 256 + (kb - 4) * 32 + lane) * 128
                                                                  : (const uint8_t*)P.wo + (blockIdx.x * 128 + (kb - 12) * 32 + lane) * 128));
        }
        if (++st == 3) { st = 0; pp ^= 1; }
      }
      if (lane == 0) STAMP(2, 1);
    } else {
      {
        const uint32_t clk0 = __shfl_sync(~0u, (uint32_t)clock(), 0), stg = sb + OFF_STG + hw * STG_STRIDE;
        const unsigned epoch = __shfl_sync(~0u, P.epoch[blockIdx.x], 0);
        const uint32_t tag = ~epoch & 1;
        uint32_t tap[2][4];
#pragma unroll
        for (int cg = 0; cg < 2; cg++) {
          const uint2 u = __ldg((const uint2*)(P.shift_k + (16 * cl + 8 * cg + g) * 4));
          tap[cg][0] = __byte_perm(u.x, 0, 0x1010); tap[cg][1] = __byte_perm(u.x, 0, 0x3232);
          tap[cg][2] = __byte_perm(u.y, 0, 0x1010); tap[cg][3] = __byte_perm(u.y, 0, 0x3232);
        }
        if (hw == 0 && lane < 8) *(float*)(smem + OFF_D + 4 * lane) = __bfloat162float(P.D[16 * cl + 8 * rank + lane]);
        if (hw == 1) asm volatile("prefetch.global.L2 [%0];" ::"l"(P.thr + (lane + 32 * (blockIdx.x & 1)) * 32));
        if (hw == 0 && elect_one()) {
          *(volatile unsigned*)(smem + OFF_EPOCH) = epoch;
          mbar_expect(BAR(B_XRAW), 16384);
          mbar_expect(BAR(B_Y), 16384 + 64);
        }
        for (int i = hw * 32 + lane; i < 528; i += 96) st_tag4(P.part + (hp * 8 + mb) * 2176 + 4 * i, 0.f, 0.f, 0.f, 0.f, tag ^ 1);
        if (hw < 2 || lane < 2) st_tag4(P.kv + hp * 2176 + (4 * (hw < 2 ? 64 * mb + 32 * hw + lane : 512 + 2 * mb + lane)), 0.f, 0.f, 0.f, 0.f, tag ^ 1);
        if (lane == 0) STAMP(3, hw);
        const uint32_t xo = sb + OFF_XT + g * XT_STRIDE + rank * 2048 + q * 4;
        const int krow = 8 + (lane & 7) - (lane >> 3);
        const uint32_t ka = stg + krow * 32 + ((krow & 4) << 2), va = stg + 2304 + lane * 32 + ((lane & 4) << 2);
        int ph = 0, b = 0;
#pragma unroll 1
        for (int ci = hw - 3; ci < 16; ci += 3) {
          const uint32_t bo = b ? OFF_F2F - OFF_STG : 0, bn = b ? 0 : OFF_F2F - OFF_STG;
          if (ci + 3 < 16) {
            while (__any_sync(~0u, (uint32_t)clock() - clk0 < HSTART + (ci + 3) * PACE)) __nanosleep(64);
            if (elect_one()) {
              mbar_expect(sbar + 8 * (b ^ 1), 2304 + 2048);
              tma2d(stg + bn, &P.tmK, 16 * cl, 1024 * rank + 64 * (ci + 3) - 8, sbar + 8 * (b ^ 1));
              tma2d(stg + bn + 2304, &P.tmV, 16 * cl, 1024 * rank + 64 * (ci + 3), sbar + 8 * (b ^ 1));
            }
          }
          if (ci >= 0) {
            mbar_wait(sbar + 8 * b, (ph >> b) & 1);
            ph ^= 1 << b;
#pragma unroll 1
            for (int grp = 0; grp < 2; grp++) {
#pragma unroll
              for (int cg = 0; cg < 2; cg++) {
                const uint32_t dst = mapa(xo + (ci >> 3) * 1024 + ((ci & 7) * 4 + 2 * grp) * 16, cg), xbar = mapa(BAR(B_XRAW), cg);
                uint32_t vv[4], kk[4][4];
                ldsm4t(vv, (va ^ (cg * 16)) + bo + grp * 1024);
#pragma unroll
                for (int rg = 0; rg < 4; rg++) ldsm4t(kk[rg], (ka ^ (cg * 16)) + bo + grp * 1024 + rg * 256);
#pragma unroll
                for (int rg = 0; rg < 4; rg++)
                  vv[rg] = hmul(hadd(hadd(hadd(hmul(kk[rg][3], tap[cg][3]), hmul(kk[rg][2], tap[cg][2])), hmul(kk[rg][1], tap[cg][1])), hmul(kk[rg][0], tap[cg][0])), vv[rg]);
                if (cg == rank) {
#pragma unroll
                  for (int rg = 0; rg < 4; rg++) asm volatile("st.shared.b32 [%0], %1;" ::"r"(dst + (rg & 1) * 512 + (rg >> 1) * 16), "r"(vv[rg]) : "memory");
                } else {
#pragma unroll
                  for (int rg = 0; rg < 4; rg++) st_async(dst + (rg & 1) * 512 + (rg >> 1) * 16, vv[rg], xbar);
                }
              }
            }
          }
          b ^= 1;
        }
      }
      if (lane == 0) STAMP(3, 3 + hw);
      asm volatile("bar.sync 4, 96;" ::: "memory");
      if (hw == 0 && elect_one()) { mbar_expect(BAR(B_XT), 10240); bulk_ld(sb + OFF_F2F, P.img, 10240, BAR(B_XT)); }
      mbar_wait(BAR(B_XRAW), 0);
    }
    int e1 = 0;
#pragma unroll 1
    for (int n = hw < 0 ? 3 : 0; n < 4; n++) {
      const bool isH = n >= 3;
      const int c = isH ? (warp & 1) + 2 * (warp & 2) : hw + 3 * n;
      if (c < 8) {
        int ln;
        asm volatile("mov.u32 %0, %%laneid;" : "=r"(ln));
        uint8_t* dst = smem + (isH ? OFF_H + (c & 2) * 8192 + (c >> 2) * 8192 + (c & 1) * 4096 : OFF_XT + c * XT_STRIDE) + ((ln >> 4) * 512 + (ln & 15) * 16);
        const uint8_t* src0 = isH ? (const uint8_t*)P.h + (16 * cl + 8 * rank + c) * 4096 + ((ln & 15) * 32 + (ln & 16)) : dst;
        const uint8_t* src1 = src0 + (isH ? 512 : 256);
        uint32_t v[32];
#pragma unroll
        for (int i = 0; i < 8; i++) {
          const uint4 u = *(const uint4*)(((i & 1) ? src1 : src0) + (i >> 1) * 1024);
          v[4 * i] = u.x; v[4 * i + 1] = u.y; v[4 * i + 2] = u.z; v[4 * i + 3] = u.w;
        }
        if (isH) mbar_wait(BAR(B_XT), 0);
        const float f0 = __uint_as_float(v[0] << 16) + ((isH && ln == 0) ? *(const float*)(smem + OFF_D + 4 * c) : 0.f);
        const int e = norm_exp(v, f0);
        norm_cvt(v, f0, e);
        if (isH) mbar_wait(BAR(B_SFREE), 0);
        else if (ln == 0) smem[OFF_EX + c] = e;
        e1 = e;
#pragma unroll
        for (int i = 0; i < 8; i++)
          *(uint4*)(dst + (i >> 1) * 1024 + (i & 1) * 256) = make_uint4(v[4 * i], v[4 * i + 1], v[4 * i + 2], v[4 * i + 3]);
        if (n < 2 && elect_one()) {
          if (n == 0) mbar_expect(sbar, 4096);
          tma3d(sb + OFF_STG + 2048 * c, &P.tmQ, 16 * cl, 64 * rank, 2 * c, sbar);
        }
      }
      if (n >= 2) {
        fence_async();
        __syncwarp();
        if (lane == 0) { mbar_arrive(BAR(isH ? B_H : B_XT)); STAMP(3, (isH ? 17 : 13) + hw); }
      }
    }
#define SLOT(tab, kb) (sb + ((uint32_t)((tab) >> (4 * (kb))) & 15) * 16384)
#define LOAD_B(kb) tma4d(SLOT(SLOT_B, kb), &P.tmWo, 0, ((kb) >> 3) * 32, 2 * ((kb) & 7), 4 * cb + 2 * rank, BAR(B_FULL2 + (kb)))
#define LOAD_A(kb) bulk_ld_mc(SLOT(SLOT_A, kb) + rank * 8192, P.o + (rb * 16 + (kb)) * 1024 + rank * 512, 8192, BAR(B_FULL2 + (kb)))
    asm volatile("setmaxnreg.inc.sync.aligned.u32 104;");
    {
    int tid;
    asm volatile("mov.u32 %0, %%tid.x;" : "=r"(tid));
    const int lane = tid & 31, g = lane >> 2, q = lane & 3;
    const unsigned epoch = *(volatile unsigned*)(smem + OFF_EPOCH);
    const uint32_t tag = ~epoch & 1;
    const int pi = hw < 2 ? 64 * mb - 288 + tid : 512 + 2 * mb + (lane & 1);
    const float* psrc = P.part + hp * 8 * 2176 + 4 * pi;
    uint4 f[8];
    {
      const uint32_t s16 = (sb & 0x3FFFF) >> 4;
      const int t = tid & 127, c = 2 + (warp & 1) + 2 * (warp & 2);
      const uint4* hp4 = (const uint4*)(P.h + (16 * cl + 8 * rank + c) * 2048) + ((lane & 15) * 2 + (lane >> 4));
      uint32_t v[32];
#pragma unroll
      for (int i = 0; i < 8; i++) { const uint4 u = ld_na4(hp4 + i * 32); v[4 * i] = u.x; v[4 * i + 1] = u.y; v[4 * i + 2] = u.z; v[4 * i + 3] = u.w; }
      float kva[36];
#pragma unroll
      for (int mt = 0; mt < 2; mt++) {
        mbar_wait(BAR(B_PKRDY + mt), 0);
        wg_fence();
#pragma unroll
        for (int ks = 0; ks < 8; ks++) {
          const uint32_t o = (ks >> 2) * 1024 + mt * 512 + (ks & 3) * 128, vb = (2 * STAGE_BYTES >> 4) + o;
          wgmma_ss_n72<1, 1>(kva, dsc(s16 + o + (1 << 16), SW128), dsc(s16 + vb + (((OFF_ONES >> 4) - vb) << 16), SW128), (mt | ks) != 0);
        }
        wg_commit();
        if (mt == 0 && hw < 0) {
          mbar_wait(BAR(B_G1DONE), 0);
          if (elect_one()) {
#pragma unroll
            for (int kb = 0; kb < BEARLY; kb++) { mbar_expect(BAR(B_FULL2 + kb), 16384); LOAD_B(kb); }
          }
        }
      }
      float* pdst = P.part + (hp * 8 + mb) * 2176 + t * 4;
      float* zdst = P.part + (hp * 8 + mb) * 2176 + 2048 + (t >> 1);
      asm volatile("" : "+l"(pdst), "+l"(zdst));
      wg_wait<0>();
      keep(kva);
      if (hw < 1) {
#pragma unroll
        for (int c = 0; c < 4; c++) st_tag4(pdst + c * 512, kva[4 * c], kva[4 * c + 1], kva[4 * c + 2], kva[4 * c + 3], tag);
      } else {
#pragma unroll
        for (int c = 4; c < 8; c++) st_tag4(pdst + (c - 4) * 512, kva[4 * c], kva[4 * c + 1], kva[4 * c + 2], kva[4 * c + 3], tag);
      }
      const float z2 = __shfl_down_sync(~0u, kva[32], 4), z3 = __shfl_down_sync(~0u, kva[34], 4);
      if (!(lane & 7)) st_tag4(zdst, kva[32], kva[34], z2, z3, tag);
      if (lane == 0) mbar_arrive(BAR(B_PKFREE));
      const uint32_t cst = clock();
      if (hw == 0 && lane == 0) STAMP(3, 24);
      const float f0 = __uint_as_float(v[0] << 16) + (lane == 0 ? *(const float*)(smem + OFF_D + 4 * c) : 0.f);
      const int e = norm_exp(v, f0);
      norm_cvt(v, f0, e);
      if (hw >= 0) {
        while (__any_sync(~0u, (uint32_t)clock() - cst < PD1)) __nanosleep(20);
        if (hw == 0 && lane == 0) STAMP(3, 20);
#pragma unroll
        for (int p = 0; p < 8; p++) f[p] = ld_rlx4(psrc + p * 2176);
      }
      uint8_t* dst = smem + OFF_H + 16384 + (warp & 3) * 4096 + (lane >> 4) * 512 + (lane & 15) * 16;
#pragma unroll
      for (int i = 0; i < 8; i++)
        *(uint4*)(dst + (i >> 1) * 1024 + (i & 1) * 256) = make_uint4(v[4 * i], v[4 * i + 1], v[4 * i + 2], v[4 * i + 3]);
      if (lane < 4) {
        const int cc = c - (lane & 2);
        st_async(mapa(sb + OFF_SCALE + (8 * rank + cc) * 4, lane & 1), min(max(((lane & 2) ? e1 : e) + smem[OFF_EX + cc] - 124, 1), 254) << 23, mapa(BAR(B_Y), lane & 1));
      }
    }
#define H2_READY() do { fence_async(); __syncwarp(); if (lane == 0) mbar_arrive(BAR(B_H2)); } while (0)
    if (warp == 8) {
      H2_READY();
      mbar_wait(BAR(B_PKFREE), 0);
      {
        const uint32_t c0 = clock();
#pragma unroll 1
        for (int i = 0; i < 2 * NPRE - 2 * BEARLY; i++) {
          const int kb = (i >> 1) + BEARLY;
          while (__any_sync(~0u, (uint32_t)clock() - c0 < i * BPACE)) __nanosleep(32);
          if (elect_one()) {
            if (!(i & 1)) mbar_expect(BAR(B_FULL2 + kb), 16384);
            tma4d(SLOT(SLOT_B, kb) + (i & 1) * 8192, &P.tmWo1, 0, 0, 2 * kb, 4 * cb + 2 * rank + (i & 1), BAR(B_FULL2 + kb));
            if (i == 0) mbar_expect(BAR(B_Q), 8192);
            if (i < 4) tma3d(sb + OFF_SPARE + 2048 * i, &P.tmQ, 16 * cl, 64 * rank + 32 * (i >> 1), 2 * ((i + 6) & 7), BAR(B_Q));
          }
        }
      }
      if (lane == 0) STAMP(2, 2);
      mbar_wait(BAR(B_AFREE), 0);
      if (elect_one()) mbar_expect(BAR(B_FULL2), 16384);
      {
        const uint32_t dst = SLOT(SLOT_A, 0) + rank * 8192;
        const uint4* src = P.o + rb * 16 * 1024 + rank * 512;
        poll_ge(&P.ocnt[rb * 32], 16 * (epoch + 1));
        asm volatile("fence.proxy.async.global;" ::: "memory");
        if (lane == 0) STAMP(2, 3);
        if (elect_one()) bulk_ld_mc(dst, src, 8192, BAR(B_FULL2));
        if (lane == 0) STAMP(3, 23);
      }
#pragma unroll 1
      for (int kb = 1; kb < NPRE; kb++) {
        mbar_wait(BAR(kb < 4 ? B_AFREE + kb - 1 : B_CONS2), 0);
        if (elect_one()) { mbar_expect(BAR(B_FULL2 + kb), 16384); LOAD_A(kb); }
      }
#pragma unroll 1
      for (int kb = NPRE; kb < 16; kb++) {
        mbar_wait(BAR(B_CONS2 + kb - 5), 0);
        if (kb == 8) mbar_wait(BAR(B_O1RDY), 0);
        if (elect_one()) { mbar_expect(BAR(B_FULL2 + kb), 32768); LOAD_A(kb); LOAD_B(kb); }
      }
      if (lane == 0) { P.epoch[blockIdx.x] = epoch + 1; STAMP(2, 5); }
    } else {
      {
#pragma unroll 1
        for (int n = 0; __any_sync(~0u, stale8(f, tag) & 1); n++) {
#pragma unroll
          for (int p = 0; p < 8; p++) ld_stale4(f[p], psrc + p * 2176, tag);
          if (n > SPIN_LIMIT) __trap();
        }
        float s0 = 0.f, s1 = 0.f, s2 = 0.f, s3 = 0.f;
#pragma unroll
        for (int p = 0; p < 8; p++) { s0 += __uint_as_float(f[p].x); s1 += __uint_as_float(f[p].y); s2 += __uint_as_float(f[p].z); s3 += __uint_as_float(f[p].w); }
        if (hw < 2 || lane < 2) st_tag4(P.kv + hp * 2176 + (4 * pi), s0, s1, s2, s3, tag);
      }
      const uint32_t cs2 = clock();
      if (lane == 0 && hw == 0) STAMP(3, 8);
      H2_READY();
      if (hw == 2) {
        unsigned* cnt = P.ocnt + (2 * mb + lane) * 32;
#pragma unroll 1
        for (int hh = 0; hh < 2; hh++) {
          mbar_wait(BAR(hh ? B_ODONE1 : B_ODONE), 0);
          if (lane < 2) asm volatile("red.release.gpu.global.add.u32 [%0], 1;" ::"l"(cnt + hh * 512) : "memory");
          if (lane == 0) STAMP(3, hh ? 6 : 7);
        }
        poll_ge(&P.ocnt[512 + rb * 32], 16 * (epoch + 1));
        asm volatile("fence.proxy.async.global;" ::: "memory");
        if (lane == 0) { mbar_arrive(BAR(B_O1RDY)); STAMP(2, 4); }
        __syncwarp();
      } else {
        const int t = tid - 288;
        const float* src = P.kv + hp * 2176 + (4 * t);
        const float* zsrc = P.kv + hp * 2176 + (2048 + (t & 48) + 2 * (lane & 6));
        while (__any_sync(~0u, (uint32_t)clock() - cs2 < PD2)) __nanosleep(20);
        uint4 zp = ld_rlx4(zsrc);
#pragma unroll
        for (int p = 0; p < 8; p++) f[p] = ld_rlx4(src + 4 * ((p & 3) * 128 + (p >> 2) * 64));
        if (!opaque_true()) __trap();
#pragma unroll 1
        for (int n = 0; __any_sync(~0u, (stale8(f, tag) | (zp.x ^ tag)) & 1); n++) {
          ld_stale4(zp, zsrc, tag);
#pragma unroll
          for (int p = 0; p < 8; p++) ld_stale4(f[p], src + 4 * ((p & 3) * 128 + (p >> 2) * 64), tag);
          if (n > SPIN_LIMIT) __trap();
        }
#define PK2U(a, b) pk2(__uint_as_float(a), __uint_as_float(b))
        const uint32_t zf = (lane & 1) ? ((lane & 8) ? zp.w : zp.z) : ((lane & 8) ? zp.y : zp.x);
        const uint32_t zz = PK2U(zf, zf);
        *(uint4*)(smem + OFF_KVB + hw * 2560 + 2048 + lane * 16) = make_uint4(zz, zz, zz, zz);
#pragma unroll
        for (int hh = 0; hh < 2; hh++) {
          const uint4* ff = &f[4 * hh];
          uint8_t* dst = smem + OFF_KVB + hh * 2560 + q * 512 + (16 * hw + g) * 16;
          *(uint4*)dst = make_uint4(PK2U(ff[0].x, ff[0].y), PK2U(ff[1].x, ff[1].y), PK2U(ff[2].x, ff[2].y), PK2U(ff[3].x, ff[3].y));
          *(uint4*)(dst + 128) = make_uint4(PK2U(ff[0].z, ff[0].w), PK2U(ff[1].z, ff[1].w), PK2U(ff[2].z, ff[2].w), PK2U(ff[3].z, ff[3].w));
        }
        fence_async();
        __syncwarp();
        if (lane == 0) { mbar_arrive(BAR(B_KV)); if (hw == 0) STAMP(3, 9); }
      }
#define QBUF(ci) (sb + 2048 * (ci) + ((ci) < 6 ? OFF_STG : (ci) < 10 ? OFF_SPARE - 6 * 2048 : OFF_F2F - 10 * 2048))
      mbar_wait(BAR(B_Y), 0);
      if (elect_one()) {
        mbar_expect(sbar + 8, 4096);
#pragma unroll 1
        for (int ci = hw ? hw + 9 : 12; ci < 16; ci += 3) tma3d(QBUF(ci), &P.tmQ, 16 * cl, 64 * rank + 32, 2 * (ci & 7), sbar + 8);
      }
      mbar_wait(BAR(B_Q), 0);
      mbar_wait(sbar, hw == 0);
      {
        const float2 sc0 = *(const float2*)(smem + OFF_SCALE + 8 * q), sc1 = *(const float2*)(smem + OFF_SCALE + 32 + 8 * q);
        const uint32_t yl = sb + OFF_XT + (lane & 7) * XT_STRIDE + (lane >> 3) * 16;
#pragma unroll 1
        for (int ci = hw; ci < 16; ci += 3) {
          const uint32_t qb = QBUF(ci);
          if (ci >= 10) mbar_wait(sbar + 8, 1);
#pragma unroll 1
          for (int nl = 0; nl < 2; nl++) {
            uint32_t yy[2][4], qq[2][4];
            const uint32_t qa = qb + lane * 32 + ((lane & 4) << 2) + nl * 1024;
#pragma unroll
            for (int cg = 0; cg < 2; cg++) { ldsm4t(yy[cg], yl + cg * 2048 + (2 * ci + nl) * 64); ldsm4(qq[cg], qa ^ (cg * 16)); }
#pragma unroll
            for (int cg = 0; cg < 2; cg++) {
              const float2 sc = cg ? sc1 : sc0;
#pragma unroll
              for (int m = 0; m < 4; m++) {
                const float2 f = __half22float2(*(const __half2*)&yy[cg][m]);
                qq[cg][m] = hmul(qq[cg][m], pk2(f.x * sc.x, f.y * sc.y));
              }
              stsm4(qa ^ (cg * 16), qq[cg][0], qq[cg][1], qq[cg][2], qq[cg][3]);
            }
          }
          fence_async();
          __syncwarp();
          if (elect_one()) tma3d_st(&P.tmOA, qb, 16 * cl, 64 * rank + 32 * (ci >> 3), 2 * (ci & 7));
        }
        asm volatile("cp.async.bulk.commit_group;\ncp.async.bulk.wait_group.read 0;" ::: "memory");
      }
      if (lane == 0) STAMP(3, 10 + hw);
    }
    }
  }
}

typedef CUresult (*EncodeFn)(CUtensorMap*, CUtensorMapDataType, cuuint32_t, void*, const cuuint64_t*, const cuuint64_t*,
                             const cuuint32_t*, const cuuint32_t*, CUtensorMapInterleave, CUtensorMapSwizzle,
                             CUtensorMapL2promotion, CUtensorMapFloatOOBfill);

static void enc(EncodeFn fn, CUtensorMap* m, const void* p, int rank, const cuuint64_t* dims, const cuuint64_t* strides,
                const cuuint32_t* box, CUtensorMapSwizzle swz, CUtensorMapL2promotion promo) {
  cuuint32_t es[4] = {1, 1, 1, 1};
  fn(m, CU_TENSOR_MAP_DATA_TYPE_BFLOAT16, rank, (void*)p, dims, strides, box, es, CU_TENSOR_MAP_INTERLEAVE_NONE, swz, promo,
     CU_TENSOR_MAP_FLOAT_OOB_FILL_NONE);
}

extern "C" void kernel_launch(void* const* d_in, const int* in_sizes, int n_in, void* d_out, int out_size) {
  void* fp = nullptr;
  cudaDriverEntryPointQueryResult qr;
  cudaGetDriverEntryPoint("cuTensorMapEncodeTiled", &fp, cudaEnableDefault, &qr);
  EncodeFn fn = (EncodeFn)fp;
  Params P;
  P.shift_k = (const __nv_bfloat16*)d_in[3]; P.h = (const __nv_bfloat16*)d_in[4]; P.D = (const __nv_bfloat16*)d_in[5];
  P.q = (const __nv_bfloat16*)d_in[0];
  cudaGetSymbolAddress((void**)&P.part, g_part); cudaGetSymbolAddress((void**)&P.kv, g_kv); cudaGetSymbolAddress((void**)&P.o, g_o);
  cudaGetSymbolAddress((void**)&P.ocnt, g_ocnt); cudaGetSymbolAddress((void**)&P.epoch, g_epoch);
  cudaGetSymbolAddress((void**)&P.thr, c_thr); cudaGetSymbolAddress((void**)&P.img, c_img);
  P.x = (const __nv_bfloat16*)d_in[6]; P.w = (const __nv_bfloat16*)d_in[7]; P.wo = (const __nv_bfloat16*)d_in[8];
  const CUtensorMapSwizzle S128 = CU_TENSOR_MAP_SWIZZLE_128B, S32 = CU_TENSOR_MAP_SWIZZLE_32B;
  const CUtensorMapL2promotion P0 = CU_TENSOR_MAP_L2_PROMOTION_NONE, P128 = CU_TENSOR_MAP_L2_PROMOTION_L2_128B;
  { cuuint64_t d[2] = {1024, 2048}, s[1] = {2048}; cuuint32_t b[2] = {64, 128}; enc(fn, &P.tmX, d_in[6], 2, d, s, b, S128, P128); }
  { cuuint64_t d[3] = {1024, 1024, 3}, s[2] = {6144, 2048}; cuuint32_t b[3] = {64, 64, 3}; enc(fn, &P.tmW, d_in[7], 3, d, s, b, S128, P128); }
  { cuuint64_t d[4] = {64, 64, 16, 16}, s[3] = {2048, 131072, 128}; cuuint32_t b[4] = {64, 32, 2, 2}; enc(fn, &P.tmWo, d_in[8], 4, d, s, b, S128, P128); }
  { cuuint64_t d[4] = {64, 64, 16, 16}, s[3] = {2048, 131072, 128}; cuuint32_t b[4] = {64, 32, 2, 1}; enc(fn, &P.tmWo1, d_in[8], 4, d, s, b, S128, P128); }
  { cuuint64_t d[2] = {1024, 2048}, s[1] = {2048}; cuuint32_t b[2] = {16, 72}; enc(fn, &P.tmK, d_in[1], 2, d, s, b, S32, P128); }
  { cuuint64_t d[2] = {1024, 2048}, s[1] = {2048}; cuuint32_t b[2] = {16, 64}; enc(fn, &P.tmV, d_in[2], 2, d, s, b, S32, P128); }
  { cuuint64_t d[3] = {1024, 128, 16}, s[2] = {32768, 2048}; cuuint32_t b[3] = {16, 32, 2}; enc(fn, &P.tmQ, d_in[0], 3, d, s, b, S32, P128); }
  { cuuint64_t d[3] = {1024, 128, 16}, s[2] = {65536, 4096}; cuuint32_t b[3] = {16, 32, 2}; enc(fn, &P.tmOA, d_out, 3, d, s, b, S32, P0); }
  { cuuint64_t d[2] = {2048, 2048}, s[1] = {4096}; cuuint32_t b[2] = {64, 16}; enc(fn, &P.tmOB, d_out, 2, d, s, b, S128, P0); }
  cudaFuncSetAttribute(fused_kernel, cudaFuncAttributeMaxDynamicSharedMemorySize, SMEM_TOTAL);
  fused_kernel<<<128, 384, SMEM_TOTAL>>>(P);
}
```

```cpp
#include <cuda_runtime.h>
#include <cuda_bf16.h>
#include <cuda_fp16.h>
#include <cuda.h>
#include <stdint.h>

template<int TA, int TB, int SA=1> __device__ __forceinline__ void wgmma_ss_n192(float (&d)[96], uint64_t da, uint64_t db, int scale_d) {
  asm volatile("{\n.reg .pred p;\nsetp.ne.b32 p, %98, 0;\n"
    "wgmma.mma_async.sync.aligned.m64n192k16.f32.bf16.bf16 {%0, %1, %2, %3, %4, %5, %6, %7, %8, %9, %10, %11, %12, %13, %14, %15, %16, %17, %18, %19, %20, %21, %22, %23, %24, %25, %26, %27, %28, %29, %30, %31, %32, %33, %34, %35, %36, %37, %38, %39, %40, %41, %42, %43, %44, %45, %46, %47, %48, %49, %50, %51, %52, %53, %54, %55, %56, %57, %58, %59, %60, %61, %62, %63, %64, %65, %66, %67, %68, %69, %70, %71, %72, %73, %74, %75, %76, %77, %78, %79, %80, %81, %82, %83, %84, %85, %86, %87, %88, %89, %90, %91, %92, %93, %94, %95}, %96, %97, p, %101, 1, %99, %100;\n}\n"
    : "+f"(d[0]), "+f"(d[1]), "+f"(d[2]), "+f"(d[3]), "+f"(d[4]), "+f"(d[5]), "+f"(d[6]), "+f"(d[7]), "+f"(d[8]), "+f"(d[9]), "+f"(d[10]), "+f"(d[11]), "+f"(d[12]), "+f"(d[13]), "+f"(d[14]), "+f"(d[15]), "+f"(d[16]), "+f"(d[17]), "+f"(d[18]), "+f"(d[19]), "+f"(d[20]), "+f"(d[21]), "+f"(d[22]), "+f"(d[23]), "+f"(d[24]), "+f"(d[25]), "+f"(d[26]), "+f"(d[27]), "+f"(d[28]), "+f"(d[29]), "+f"(d[30]), "+f"(d[31]), "+f"(d[32]), "+f"(d[33]), "+f"(d[34]), "+f"(d[35]), "+f"(d[36]), "+f"(d[37]), "+f"(d[38]), "+f"(d[39]), "+f"(d[40]), "+f"(d[41]), "+f"(d[42]), "+f"(d[43]), "+f"(d[44]), "+f"(d[45]), "+f"(d[46]), "+f"(d[47]), "+f"(d[48]), "+f"(d[49]), "+f"(d[50]), "+f"(d[51]), "+f"(d[52]), "+f"(d[53]), "+f"(d[54]), "+f"(d[55]), "+f"(d[56]), "+f"(d[57]), "+f"(d[58]), "+f"(d[59]), "+f"(d[60]), "+f"(d[61]), "+f"(d[62]), "+f"(d[63]), "+f"(d[64]), "+f"(d[65]), "+f"(d[66]), "+f"(d[67]), "+f"(d[68]), "+f"(d[69]), "+f"(d[70]), "+f"(d[71]), "+f"(d[72]), "+f"(d[73]), "+f"(d[74]), "+f"(d[75]), "+f"(d[76]), "+f"(d[77]), "+f"(d[78]), "+f"(d[79]), "+f"(d[80]), "+f"(d[81]), "+f"(d[82]), "+f"(d[83]), "+f"(d[84]), "+f"(d[85]), "+f"(d[86]), "+f"(d[87]), "+f"(d[88]), "+f"(d[89]), "+f"(d[90]), "+f"(d[91]), "+f"(d[92]), "+f"(d[93]), "+f"(d[94]), "+f"(d[95])
    : "l"(da), "l"(db), "r"(scale_d), "n"(TA), "n"(TB), "n"(SA));
}
template<int TA, int TB, int SA=1> __device__ __forceinline__ void wgmma_ss_n128(float (&d)[64], uint64_t da, uint64_t db, int scale_d) {
  asm volatile("{\n.reg .pred p;\nsetp.ne.b32 p, %66, 0;\n"
    "wgmma.mma_async.sync.aligned.m64n128k16.f32.bf16.bf16 {%0, %1, %2, %3, %4, %5, %6, %7, %8, %9, %10, %11, %12, %13, %14, %15, %16, %17, %18, %19, %20, %21, %22, %23, %24, %25, %26, %27, %28, %29, %30, %31, %32, %33, %34, %35, %36, %37, %38, %39, %40, %41, %42, %43, %44, %45, %46, %47, %48, %49, %50, %51, %52, %53, %54, %55, %56, %57, %58, %59, %60, %61, %62, %63}, %64, %65, p, %69, 1, %67, %68;\n}\n"
    : "+f"(d[0]), "+f"(d[1]), "+f"(d[2]), "+f"(d[3]), "+f"(d[4]), "+f"(d[5]), "+f"(d[6]), "+f"(d[7]), "+f"(d[8]), "+f"(d[9]), "+f"(d[10]), "+f"(d[11]), "+f"(d[12]), "+f"(d[13]), "+f"(d[14]), "+f"(d[15]), "+f"(d[16]), "+f"(d[17]), "+f"(d[18]), "+f"(d[19]), "+f"(d[20]), "+f"(d[21]), "+f"(d[22]), "+f"(d[23]), "+f"(d[24]), "+f"(d[25]), "+f"(d[26]), "+f"(d[27]), "+f"(d[28]), "+f"(d[29]), "+f"(d[30]), "+f"(d[31]), "+f"(d[32]), "+f"(d[33]), "+f"(d[34]), "+f"(d[35]), "+f"(d[36]), "+f"(d[37]), "+f"(d[38]), "+f"(d[39]), "+f"(d[40]), "+f"(d[41]), "+f"(d[42]), "+f"(d[43]), "+f"(d[44]), "+f"(d[45]), "+f"(d[46]), "+f"(d[47]), "+f"(d[48]), "+f"(d[49]), "+f"(d[50]), "+f"(d[51]), "+f"(d[52]), "+f"(d[53]), "+f"(d[54]), "+f"(d[55]), "+f"(d[56]), "+f"(d[57]), "+f"(d[58]), "+f"(d[59]), "+f"(d[60]), "+f"(d[61]), "+f"(d[62]), "+f"(d[63])
    : "l"(da), "l"(db), "r"(scale_d), "n"(TA), "n"(TB), "n"(SA));
}
template<int TA, int TB, int SA=1> __device__ __forceinline__ void wgmma_ss_n72(float (&d)[36], uint64_t da, uint64_t db, int scale_d) {
  asm volatile("{\n.reg .pred p;\nsetp.ne.b32 p, %38, 0;\n"
    "wgmma.mma_async.sync.aligned.m64n72k16.f32.bf16.bf16 {%0, %1, %2, %3, %4, %5, %6, %7, %8, %9, %10, %11, %12, %13, %14, %15, %16, %17, %18, %19, %20, %21, %22, %23, %24, %25, %26, %27, %28, %29, %30, %31, %32, %33, %34, %35}, %36, %37, p, %41, 1, %39, %40;\n}\n"
    : "+f"(d[0]), "+f"(d[1]), "+f"(d[2]), "+f"(d[3]), "+f"(d[4]), "+f"(d[5]), "+f"(d[6]), "+f"(d[7]), "+f"(d[8]), "+f"(d[9]), "+f"(d[10]), "+f"(d[11]), "+f"(d[12]), "+f"(d[13]), "+f"(d[14]), "+f"(d[15]), "+f"(d[16]), "+f"(d[17]), "+f"(d[18]), "+f"(d[19]), "+f"(d[20]), "+f"(d[21]), "+f"(d[22]), "+f"(d[23]), "+f"(d[24]), "+f"(d[25]), "+f"(d[26]), "+f"(d[27]), "+f"(d[28]), "+f"(d[29]), "+f"(d[30]), "+f"(d[31]), "+f"(d[32]), "+f"(d[33]), "+f"(d[34]), "+f"(d[35])
    : "l"(da), "l"(db), "r"(scale_d), "n"(TA), "n"(TB), "n"(SA));
}
template<int TB, int SA=1> __device__ __forceinline__ void wgmma_rs_n40(float (&d)[20], uint32_t a0, uint32_t a1, uint32_t a2, uint32_t a3, uint64_t db, int scale_d) {
  asm volatile("{\n.reg .pred p;\nsetp.ne.b32 p, %25, 0;\n"
    "wgmma.mma_async.sync.aligned.m64n40k16.f32.bf16.bf16 {%0, %1, %2, %3, %4, %5, %6, %7, %8, %9, %10, %11, %12, %13, %14, %15, %16, %17, %18, %19}, {%20, %21, %22, %23}, %24, p, %27, 1, %26;\n}\n"
    : "+f"(d[0]), "+f"(d[1]), "+f"(d[2]), "+f"(d[3]), "+f"(d[4]), "+f"(d[5]), "+f"(d[6]), "+f"(d[7]), "+f"(d[8]), "+f"(d[9]), "+f"(d[10]), "+f"(d[11]), "+f"(d[12]), "+f"(d[13]), "+f"(d[14]), "+f"(d[15]), "+f"(d[16]), "+f"(d[17]), "+f"(d[18]), "+f"(d[19])
    : "r"(a0), "r"(a1), "r"(a2), "r"(a3), "l"(db), "r"(scale_d), "n"(TB), "n"(SA));
}
template<int TB> __device__ __forceinline__ void wgmma_hrs_n64(uint32_t (&d)[16], uint32_t a0, uint32_t a1, uint32_t a2, uint32_t a3, uint64_t db, int scale_d) {
  asm volatile("{\n.reg .pred p;\nsetp.ne.b32 p, %21, 0;\n"
    "wgmma.mma_async.sync.aligned.m64n64k16.f16.f16.f16 {%0, %1, %2, %3, %4, %5, %6, %7, %8, %9, %10, %11, %12, %13, %14, %15}, {%16, %17, %18, %19}, %20, p, 1, 1, %22;\n}\n"
    : "+r"(d[0]), "+r"(d[1]), "+r"(d[2]), "+r"(d[3]), "+r"(d[4]), "+r"(d[5]), "+r"(d[6]), "+r"(d[7]), "+r"(d[8]), "+r"(d[9]), "+r"(d[10]), "+r"(d[11]), "+r"(d[12]), "+r"(d[13]), "+r"(d[14]), "+r"(d[15])
    : "r"(a0), "r"(a1), "r"(a2), "r"(a3), "l"(db), "r"(scale_d), "n"(TB));
}
template<int TB> __device__ __forceinline__ void wgmma_hrs_n32(uint32_t (&d)[8], uint32_t a0, uint32_t a1, uint32_t a2, uint32_t a3, uint64_t db, int scale_d) {
  asm volatile("{\n.reg .pred p;\nsetp.ne.b32 p, %13, 0;\n"
    "wgmma.mma_async.sync.aligned.m64n32k16.f16.f16.f16 {%0, %1, %2, %3, %4, %5, %6, %7}, {%8, %9, %10, %11}, %12, p, 1, 1, %14;\n}\n"
    : "+r"(d[0]), "+r"(d[1]), "+r"(d[2]), "+r"(d[3]), "+r"(d[4]), "+r"(d[5]), "+r"(d[6]), "+r"(d[7])
    : "r"(a0), "r"(a1), "r"(a2), "r"(a3), "l"(db), "r"(scale_d), "n"(TB));
}

__device__ __align__(128) const uint32_t c_thr[1536] = {
  0x33fb33ff,0xa49c9de4,0x33273352,0xaf2cae76,0x33e233f1,0xa96ca7bd,0x32c432f7,0xb045afdd,0x33b733cf,0xac3eaaf7,0x3250328c,0xb0eab099,
  0x3378339a,0xadbcacff,0x31cd3211,0xb182b137,0x33d033fb,0xaadea46a,0x299e2d17,0xb3e0b396,0x32fb337a,0xafd2adb1,0xa78b1f76,0xb3f2b3ff,
  0x318b3254,0xb1c5b0e5,0xae6bac32,0xb354b3b8,0x2f4230a3,0xb321b285,0xb133b040,0xb215b2c7,0x337c33f2,0xada5a759,0xb179afc8,0xb1d6b2fe,
  0x31463293,0xb204b08e,0xb394b2ba,0xad23b055,0x2b402f4e,0xb3cbb31e,0xb3e4b3f9,0x293ba533,0xac269c52,0xb3bab400,0xb258b357,0x30e02e5f,
  0x330133e5,0xafbda922,0xb3f3b3c9,0x2727ab59,0x2deb314a,0xb36fb200,0xb194b32f,0x31bc2f0a,0xacdb2084,0xb39fb3ff,0xa565aea4,0x33f93347,
  0xb2b6b0db,0xb05ab25c,0x30892c1a,0x329733bc,0x326033d4,0xb0d6aa94,0xb00ab29b,0x32e83084,0x20e82f64,0xb3feb318,0x2d8da597,0x338133f8,
  0xb1fcae48,0xb14fb35c,0x339031b8,0x2d3a3199,0xb3e6b3ae,0x2909ac7b,0x32d133f4,0xb030a6f5,0x319d33bf,0xb1b3ac02,0x2e3ca874,0x335e33ec,
  0xacc32b89,0xb3a3b3c6,0x33f83276,0x25c930b7,0xb3dcb1f8,0xaa01b154,0x30653335,0xb2b0aef4,0xb107b383,0x32392d81,0xafa6214d,0xb307b3fe,
  0x30bc33a5,0xb273acb7,0x33c5311b,0x2ba23229,0xb0cc94b6,0xb267b400,0x30153360,0xb2e1ae31,0xb385b3ab,0x2d76ac93,0xb166a691,0xb1e7b3f5,
  0x22deb06a,0x33fd32ac,0xb337b3da,0x2ee8aa19,0x2f853387,0xb310ad6a,0x322d33fe,0xb1162216,0xb2a9abd3,0xb06fb3c2,0xb07428a6,0xb2a5b3ea,
  0xb111b3e9,0x323128be,0xb30db3c3,0x2f90abba,0x31aa227a,0x31a633fd,0x2e25ad5e,0x33633389,0x2d6a3365,0xb387ae1a,0xa21631aa,0xb3feb1a6,
  0xb3c2af85,0xabd3b310,0xb3eab22d,0x28a6b116,0xa8beb2a9,0x33e9306f,0x2bbab074,0x33c332a5,0x33fd3111,0x227a3231,0x3389330d,0xad5e2f90,
  0x2a63333f,0xb3d7aec6,0xb2a2a1b1,0xb07ab3fe,0xb3f7b158,0x25fbb1f4,0xacb7b38b,0x33a52d52,0x2e0eb025,0x336832d8,0x340030bc,0x14b63273,
  0x323533c0,0xb10c2beb,0xac9330cc,0xb3abb267,0x23433316,0xb3fdaf6f,0xb38eb225,0x2d46b11f,0xb342b29e,0x2ebbb07f,0x31e3aa7c,0x316b33d6,
  0x3264a6c3,0x30d133f5,0x2c0233ac,0xb3bfac87,0x28f0336a,0xb3e7ae02,0xb3c6b19d,0x2b89b1b3,0xa59732e8,0xb3f8b00a,0xaccfb3ed,0x33a1285b,
  0xb1b8b381,0x3199ad8d,0x336c31df,0xadf73170,0x33f42d3a,0x26f53390,0xb30423a7,0xafb2b3fc,0xb05f3030,0xb2b3b2d1,0x29e8b27a,0x33dd30b2,
  0xab5932b6,0xb3c9b05a,0x30adb089,0x327e3297,0xaf0ab3f3,0x332fa727,0x240633b0,0xb3fcac6f,0x33473194,0xaea431bc,0xb174b359,0x31daae54,
  0xb3bca565,0xac1ab3f9,0x33ee2f59,0xa842331b,0xaddf3281,0xb371b0a8,0x34002b40,0x1c5233cb,0xa759b3ef,0x33f22829,0xb2fe2c26,0xafc8b3ba,
  0x308e337c,0xb2932da5,0x3055b179,0x32ba31d6,0xb31eb146,0x2f4eb204,0xa5333394,0xb3f9ad23,0xaff33249,0xb2f1b0f3,0x30e532fb,0xb2542fd2,
  0x2b28b373,0x33cc2dd4,0xb285b18b,0x30a3b1c5,0x246a33fa,0xb3fba500,0x33962f42,0xad173321,0xadb1b3d0,0x337aaade,0xb3ffa99e,0x1f76b3e0,
  0xb0ee320d,0xb24db13c,0xac4b3398,0xb3b5ad0b,0x304ab289,0x32c1309e,0x2985b3ce,0x33e12b0f,0xaf3732f4,0xb324afe8,0xa4ce33f0,0xb3faa7ef,
  0x2dc8b34f,0x33762e82,0x9de4b3ff,0x33ff1ead,0xb1c931cd,0xb186b182,0xb3762e82,0xadc8b34f,0x324db13c,0x30ee320d,0x33b5ad0b,0x2c4b3398,
  0xb2c1309e,0xb04ab289,0xb3e12b0f,0xa985b3ce,0x3324afe8,0x2f3732f4,0x33faa7ef,0x24ce33f0,0xb285318b,0xb0a3b1c5,0xb2c7ae6b,0x3040b354,
  0x3396af42,0x2d173321,0x31413133,0xb2093215,0xb3ff299e,0x9f76b3e0,0xae8db2bd,0x334cb050,0x33b8278b,0xac3233f2,0x281033b3,0xb3ef2c57,
  0xb31e3146,0xaf4eb204,0xa533b394,0x33f9ad23,0x3400ab40,0x9c5233cb,0xae5f33e4,0xb357a93b,0xb2feac26,0x2fc8b3ba,0x3245b258,0x30f830e0,
  0x30553179,0xb2ba31d6,0xb3df2e99,0xa9b6b34a,0xb39230fd,0xad2fb241,0x3200b301,0x314a2fbd,0x337f1b11,0xad993400,0xb3ff2deb,0xa084b36f,
  0xb005b129,0x32ebb21d,0x325c2cdb,0xb0db339f,0xa92233de,0xb3e529cf,0xab59b2b6,0x33c9b05a,0xb3dd30b2,0xa9e8b27a,0x33d4ab71,0xaa9433c8,
  0x32212c0e,0xb12433bd,0xaf64b0d6,0x3318b260,0x197fb345,0x3400aeaf,0xae4833fe,0xb35c20e8,0xb23d3332,0xb102aeff,0x33aeb14f,0x2c7b31fc,
  0xb3fe3065,0xa14db2b0,0x2ebb307f,0xb342329e,0x300f2fa6,0xb2e53307,0x30d1b3f5,0x326426c3,0x302ab400,0x32d517db,0xb3e72e02,0x28f0b36a,
  0xb3fd2f6f,0x2343b316,0x2d46311f,0xb38e3225,0xb3f53015,0x2691b2e1,0xaf9b33eb,0xb30a288d,0x2a193166,0xb3da31e7,0x33d7aec6,0xaa63333f,
  0x3313b337,0x2f7a2ee8,0xa5fbb1f4,0x33f7b158,0xb1a1a8d7,0x31afb3e8,0xb36832d8,0xae0eb025,0xb3c22f85,0x2bd3b310,0xb3ea322d,0xa8a6b116,
  0xa8be32a9,0xb3e9306f,0x2bba3074,0xb3c332a5,0x33fdb111,0xa27a3231,0x3389b30d,0x2d5e2f90,0xa216b1aa,0x33feb1a6,0xaed2ae25,0x333db363,
  0xb3652edd,0x2e1ab33a,0xb1aa227a,0x31a6b3fd,0xaf853387,0xb3102d6a,0xb22d33fe,0xb116a216,0x32a9abd3,0xb06f33c2,0x307428a6,0xb2a533ea,
  0x3111b3e9,0x3231a8be,0x330db3c3,0x2f902bba,0xb2e12e31,0x3015b360,0x288db1a1,0x33ebb1af,0xb1e733f5,0xb1662691,0xb33f2f9b,0x2ec6b30a,
  0x2ee82a19,0xb33733da,0xb15833d7,0xb1f42a63,0x33e8b313,0x28d72f7a,0x302525fb,0xb2d833f7,0xb2392d81,0x3107b383,0x3307b3fe,0x2fa6214d,
  0xb35e33ec,0xae3ca874,0x97dbb00f,0x3400b2e5,0xa5c930b7,0xb3f83276,0xb316302a,0x2f6fb2d5,0x32b0aef4,0xb0653335,0xb29e33fd,0xb07f2343,
  0xb1702ccf,0x31dfb3a1,0x3345b124,0xaeaf3221,0xb3fc336c,0xa3a7adf7,0x3332b400,0x2eff997f,0xb0b23304,0xb27a2fb2,0x2b71b102,0x33c8b23d,
  0x2c0e29e8,0xb3bd33dd,0xb0d62a94,0x3260b3d4,0xb0892c1a,0x3297b3bc,0x2aad2842,0xb3d333ee,0xb3b0327e,0x2c6fb0ad,0x3241b035,0xb0fd32ce,
  0xb35933fc,0xae542406,0x3400b392,0x1b112d2f,0xaf5931da,0xb31b3174,0x321db37f,0x3129ad99,0xaf152ac6,0x332cb3d2,0xb1463293,0xb204308e,
  0xb281312e,0x30a8b219,0xab402f4e,0xb3cb331e,0xb3ef3371,0x2829addf,0x2c269c52,0xb3ba3400,0xb37c33f2,0xada52759,0x3179afc8,0xb1d632fe,
  0xacf32953,0x339cb3e3,0xb3fa33cc,0x2500ab28,0xb0942f21,0x3290b32a,0xb3d033fb,0xaade246a,0xb249317d,0x30f3b1d2,0xb2fb337a,0xafd22db1,
  0xb37332f1,0x2dd4aff3,0xb18b3254,0xb1c530e5,0xa96c27bd,0x33e2b3f1,0xb0452fdd,0x32c4b2f7,0xac3e2af7,0x33b7b3cf,0xb0ea3099,0x3250b28c,
  0xadbc2cff,0x3378b39a,0xb1823137,0x31cdb211,0xaf2c2e76,0x3327b352,0xb20d31c9,0x313cb186,0x313c3186,0xb20db1c9,0x2d0b2dc8,0xb398b376,
  0x309e30ee,0xb289b24d,0x2b0f2c4b,0xb3ceb3b5,0x2fe8304a,0xb2f4b2c1,0x27ef2985,0xb3f0b3e1,0x2e822f37,0xb34fb324,0x1ead24ce,0xb3ffb3fa,
  0xb2bdb209,0xb050b141,0xb290b32a,0x30942f21,0xb3b3b34c,0xac57ae8d,0xb0f3b1d2,0x3249317d,0xb400b3ef,0x1d1ba810,0xadd4aff3,0x337332f1,
  0xb39cb3e3,0x2cf32953,0xa500ab28,0x33fa33cc,0xae99b0f8,0x334a3245,0x33ff33b2,0x201f2c63,0x2438a9b6,0x33fc33df,0x332c33d2,0xaf15aac6,
  0x303a2ce7,0x32cb339e,0x30a83219,0xb281b12e,0x32ee31c0,0x2ffe3190,0x28292ddf,0xb3efb371,0x33b0327e,0x2c6f30ad,0xb241b035,0xb0fdb2ce,
  0x335933fc,0xae54a406,0xb400b392,0x1b11ad2f,0x2f5931da,0xb31bb174,0xb21db37f,0x31292d99,0xaaad2842,0xb3d3b3ee,0xa9cfb005,0x33de32eb,
  0x285b305f,0xb3edb2b3,0x2c0ea9e8,0x33bd33dd,0xb170accf,0xb1dfb3a1,0x33453124,0x2eaf3221,0xb3fcb36c,0x23a7adf7,0x33323400,0xaeff997f,
  0xb0b2b304,0x327a2fb2,0x2b713102,0xb3c8b23d,0xb400b2e5,0x17dbb00f,0x2e023264,0xb36ab0d1,0xaf6fb2d5,0x3316302a,0xb11fa8f0,0xb225b3e7,
  0x307f2343,0x329e33fd,0xb3d6b38e,0x2a7cad46,0x33f53342,0xa6c32ebb,0xac87b1e3,0x33ac316b,0x28d7af7a,0x33e83313,0xb2d8b3f7,0x3025a5fb,
  0x33eb31af,0x288d31a1,0x2bebae0e,0x33c03368,0x2ec6330a,0xb33faf9b,0x33fe3235,0x21b1310c,0xb1f4aa63,0xb158b3d7,0x2d5232a2,0xb38bb07a,
  0x33a7333d,0xacab2ed2,0x33f63162,0x262d31eb,0xaa4b301a,0xb3d8b2de,0x2a32326b,0xb3d9b0c7,0xb3f6b26f,0x265fb0c1,0xb3a9b020,0xac9fb2db,
  0x0e48b15d,0x340031f0,0xae1ab33a,0x33652edd,0xaed22e25,0xb33db363,0xb1eb0e48,0xb162b400,0xb2deb3a7,0x301aacab,0xb0c7b3f6,0x326b262d,
  0x30c1aa4b,0x326f33d8,0x32db2a32,0x302033d9,0x31f033f6,0xb15d265f,0x2edd33a9,0xb33aac9f,0xb2acb385,0x306aad76,0x2a19b166,0x33da31e7,
  0x3229a2de,0x311b33fd,0x33133337,0xaf7a2ee8,0x2e3133c5,0xb360aba2,0xb1a128d7,0xb1afb3e8,0xb3f5b015,0xa691b2e1,0xaf9bb3eb,0x330a288d,
  0x3154acc3,0x31f833a3,0x2ef433f8,0xb335a5c9,0x2d8133dc,0xb383aa01,0xb3feb065,0x214db2b0,0xb3ecb107,0x2874b239,0x300fafa6,0x32e53307,
  0x30b7ae3c,0x3276335e,0x302a3400,0xb2d517db,0x312433bd,0xb2212c0e,0xb318b260,0x2f64b0d6,0xb400aeaf,0x997fb345,0x335c20e8,0x2e4833fe,
  0x3102aeff,0x323d3332,0xac7b31fc,0xb3aeb14f,0x2a9433c8,0xb3d4ab71,0xb084b3e6,0x329ba909,0xb2ce2aad,0xb035b3d3,0x33e529cf,0x292233de,
  0x2d2fb241,0x339230fd,0xb14a2fbd,0xb200b301,0x2d993400,0xb37f1b11,0x2084b36f,0x33ff2deb,0xb2ebb21d,0x3005b129,0x30db339f,0xb25c2cdb,
  0xae5fb3e4,0x3357a93b,0xb190303a,0xb1c0b2cb,0x32453258,0xb0f830e0,0x2c63b2ee,0x33b22ffe,0xb3dfae99,0x29b6b34a,0x2ac633ff,0xb3d2a01f,
  0x339ea438,0x2ce733fc,0xb12eb32c,0x3219af15,0x33b8a78b,0x2c3233f2,0x2810b3b3,0x33ef2c57,0xb2c72e6b,0xb040b354,0x29533400,0xb3e31d1b,
  0x3141b133,0x32093215,0xaf21b39c,0x332aacf3,0xae8d32bd,0xb34cb050,0x317d3290,0xb1d23094,0x27bd33fb,0xb3f1249c,0x2fdd3327,0xb2f72f2c,
  0xaaf7b3e2,0x33cfa96c,0xb099b2c4,0x328cb045,0x2cff33b7,0xb39a2c3e,0x31373250,0xb21130ea,0xae76b378,0x3352adbc,0xb1c9b1cd,0x3186b182,
  0xb3ff1ead,0x1de4b3ff,0xb352adbc,0x2e76b378,0x33f1249c,0xa7bd33fb,0x32f72f2c,0xafdd3327,0xb3cfa96c,0x2af7b3e2,0xb28cb045,0x3099b2c4,
  0x339a2c3e,0xacff33b7,0x321130ea,0xb1373250,0x2953b400,0x33e31d1b,0x33ccadd4,0x2b283373,0xaf21339c,0xb32aacf3,0xb3fb2500,0x246ab3fa,
  0x317db290,0x31d23094,0x337a2ade,0xadb133d0,0xb2f130f3,0xaff3b249,0xb254afd2,0x30e5b2fb,0x339e2438,0xace733fc,0xb12e332c,0xb219af15,
  0xb190b03a,0x31c0b2cb,0x3371b0a8,0x2ddf3281,0x2c6332ee,0xb3b22ffe,0xb3f22829,0x2759b3ef,0x2ac6b3ff,0x33d2a01f,0x32932da5,0xb08e337c,
  0xaf0a33f3,0xb32fa727,0x2406b3b0,0x33fcac6f,0x3347b194,0x2ea431bc,0xb1743359,0xb1daae54,0xb3bc2565,0x2c1ab3f9,0x33eeaf59,0x2842331b,
  0x30ad3089,0xb27e3297,0xb2ceaaad,0x3035b3d3,0xb29ba909,0x3084b3e6,0x305f3030,0xb2b332d1,0x259732e8,0xb3f8300a,0x2ccfb3ed,0x33a1a85b,
  0x31b8b381,0x31992d8d,0xb36c31df,0xadf7b170,0xb3f42d3a,0x26f5b390,0x330423a7,0xafb233fc,0x316bb3d6,0x31e32a7c,0xb3832a01,0x2d81b3dc,
  0xb3bf2c87,0x2c02b3ac,0x28743239,0xb3ec3107,0x2b8931b3,0xb3c6319d,0x3276b35e,0x30b72e3c,0x31f8b3a3,0x31542cc3,0xb33525c9,0x2ef4b3f8,
  0x310c2beb,0xb23533c0,0x33abb267,0x2c9330cc,0x307ab3fe,0x32a2a1b1,0xb06aad76,0x32acb385,0xb3a52d52,0x2cb7b38b,0xb11b33fd,0xb229a2de,
  0x94b63273,0xb40030bc,0x3360aba2,0xae3133c5,0xb2de33a7,0xb01aacab,0xb0c733f6,0xb26b262d,0x30c12a4b,0xb26f33d8,0x32dbaa32,0xb02033d9,
  0x31f0b3f6,0x315d265f,0x2eddb3a9,0x333aac9f,0xb1eb8e48,0x3162b400,0xb3872e1a,0x2d6ab365,0xae25ad5e,0x3363b389,0x8e48b15d,0x3400b1f0,
  0xb3a7333d,0xacabaed2,0xb3f63162,0x262db1eb,0x2a4b301a,0xb3d832de,0xaa32326b,0xb3d930c7,0x33f6b26f,0x265f30c1,0x33a9b020,0xac9f32db,
  0x33c0b368,0x2beb2e0e,0x30cc94b6,0xb2673400,0x21b1b10c,0x33feb235,0x3385b3ab,0x2d762c93,0xb38b307a,0x2d52b2a2,0xa2deb06a,0x33fdb2ac,
  0xb0bc33a5,0xb2732cb7,0xb3c5311b,0x2ba2b229,0x26c32ebb,0xb3f53342,0xb3ac316b,0x2c87b1e3,0x336ab0d1,0xae023264,0xb19d33bf,0xb1b32c02,
  0x3225b3e7,0x311fa8f0,0x2cc32b89,0xb3a333c6,0xaa7cad46,0x33d6b38e,0x33dcb1f8,0xaa013154,0xb3fe3318,0x20e8af64,0x3381b3f8,0x2d8d2597,
  0xb14f335c,0xb1fc2e48,0x2d3ab199,0x3390b1b8,0x29092c7b,0xb3e633ae,0xb03026f5,0x32d1b3f4,0x32e8b084,0xb00a329b,0xb3ed32b3,0x285bb05f,
  0x29cfb005,0x33deb2eb,0xb05a325c,0xb2b630db,0xafbd2922,0x3301b3e5,0x27272b59,0xb3f333c9,0xb36f3200,0x2debb14a,0x31bcaf0a,0xb194332f,
  0xb39f33ff,0xacdba084,0x33f9b347,0xa5652ea4,0x3394b2ba,0xad233055,0xa438a9b6,0x33fcb3df,0x33e4b3f9,0x293b2533,0xb03a2ce7,0x32cbb39e,
  0x3258b357,0x30e0ae5f,0xb2ee31c0,0x2ffeb190,0x2e99b0f8,0x334ab245,0xb3ff33b2,0x201fac63,0xaf4230a3,0xb3213285,0x3133b040,0xb21532c7,
  0xa99e2d17,0xb3e03396,0x32bdb209,0xb0503141,0x278b1f76,0xb3f233ff,0x33b3b34c,0xac572e8d,0x2e6bac32,0xb35433b8,0x3400b3ef,0x1d1b2810,
  0xb289324d,0x309eb0ee,0xb3ce33b5,0x2b0fac4b,0xb2f432c1,0x2fe8b04a,0xb3f033e1,0x27efa985,0xb34f3324,0x2e82af37,0xb3ff33fa,0x1eada4ce,
  0xb3983376,0x2d0badc8,0xb3fb33ff,0xa49c1de4,0x351c35f6,0xac93a617,0xb8a3b93c,0x308d2a16,0x32f43448,0xb160afa5,0xb6a4b7fe,0x353a3389,
  0x2fa53160,0xb448b2f4,0xb389b53a,0x37fe36a4,0x26172c93,0xb5f6b51c,0xaa16b08d,0x393c38a3,0x34c3358c,0xac47a5b2,0xb85fb8f3,0x304229b1,
  0x327e33fd,0xb106af26,0xb63cb785,0x34e7330f,0x2f263106,0xb3fdb27e,0xb30fb4e7,0x3785363c,0x25b22c47,0xb58cb4c3,0xa9b1b042,0x38f3385f,
  0x346a3523,0xabf6a54d,0xb81ab8a8,0x2fef294d,0x3209336b,0xb0acaea7,0xb5d4b70a,0x34933294,0x2ea730ac,0xb36bb209,0xb294b493,0x370a35d4,
  0x254d2bf6,0xb523b46a,0xa94dafef,0x38a8381a,0x341334bc,0xab5fa4e9,0xb7a6b85a,0x2f5928e8,0x319432da,0xb052ae28,0xb56ab68d,0x343e3219,
  0x2e283052,0xb2dab194,0xb219b43e,0x368d356a,0x24e92b5f,0xb4bcb413,0xa8e8af59,0x385a37a6,0x33783456,0xaac8a484,0xb715b80a,0x2ec32884,
  0x3120324a,0xaff2ada9,0xb4ffb60e,0x33d3319e,0x2da92ff2,0xb24ab120,0xb19eb3d3,0x360e34ff,0x24842ac8,0xb456b378,0xa884aec3,0x380a3715,
  0x32cd33e3,0xaa31a420,0xb682b76f,0x2e2d281f,0x30ac31bb,0xaf3fad2a,0xb493b58d,0x33283122,0x2d2a2f3f,0xb1bbb0ac,0xb122b328,0x358d3493,
  0x24202a31,0xb3e3b2cd,0xa81fae2d,0x376f3682,0x3223331c,0xa999a376,0xb5ebb6c6,0x2d972776,0x3039312d,0xae8dacac,0xb426b50b,0x327c30a6,
  0x2cac2e8d,0xb12db039,0xb0a6b27c,0x350b3426,0x23762999,0xb31cb223,0xa776ad97,0x36c635eb,0x317a3257,0xa902a2ad,0xb552b61a,0x2d0026ad,
  0x2f8c309f,0xaddcac2e,0xb371b487,0x31cf3029,0x2c2e2ddc,0xb09faf8c,0xb029b1cf,0x34873371,0x22ad2902,0xb257b17a,0xa6adad00,0x361a3552,
  0x30d23194,0xa86ba1e4,0xb4b7b56a,0x2c6a25e4,0x2ea73012,0xad2aab5f,0xb294b402,0x31222f59,0x2b5f2d2a,0xb012aea7,0xaf59b122,0x34023294,
  0x21e4286b,0xb194b0d2,0xa5e4ac6a,0x356a34b7,0x302c30d2,0xa7a9a11b,0xb41ab4b7,0x2ba7251b,0x2dc22f0c,0xac79aa63,0xb1b6b2f7,0x30742e5f,
  0x2a632c79,0xaf0cadc2,0xae5fb074,0x32f731b6,0x211b27a9,0xb0d2b02c,0xa51baba7,0x34b7341a,0x2f0c3012,0xa67ba052,0xb2f7b402,0x2a7a2452,
  0x2cde2df5,0xab91a967,0xb0d7b1e8,0x2f8b2d65,0x29672b91,0xadf5acde,0xad65af8b,0x31e830d7,0x2052267b,0xb012af0c,0xa452aa7a,0x340232f7,
  0x2dc22ea7,0xa54d9f12,0xb1b6b294,0x294d2311,0x2bf62cde,0xaa31a86b,0xafefb0d7,0x2e2d2c6a,0x286b2a31,0xacdeabf6,0xac6aae2d,0x30d72fef,
  0x1f12254d,0xaea7adc2,0xa311a94d,0x329431b6,0x2c792d2a,0xa4209d7f,0xb074b122,0x281f217f,0x2a312b91,0xa8d0a6e0,0xae2daf8b,0x2cce2ade,
  0x26e028d0,0xab91aa31,0xaadeacce,0x2f8b2e2d,0x1d7f2420,0xad2aac79,0xa17fa81f,0x31223074,0x2a632b5f,0xa1e49bdb,0xae5faf59,0x25e41fdb,
  0x286b2967,0xa6e0a4e9,0xac6aad65,0x2ade28e8,0x24e926e0,0xa967a86b,0xa8e8aade,0x2d652c6a,0x1bdb21e4,0xab5faa63,0x9fdba5e4,0x2f592e5f,
  0x27a9286b,0x9f1298b6,0xaba7ac6a,0x23111cb6,0x254d267b,0xa420a1e4,0xa94daa7a,0x281f25e4,0x21e42420,0xa67ba54d,0xa5e4a81f,0x2a7a294d,
  0x18b61f12,0xa86ba7a9,0x9cb6a311,0x2c6a2ba7,0x211b21e4,0x98b69248,0xa51ba5e4,0x1cb61648,0x1f122052,0x9d7f9bdb,0xa311a452,0x217f1fdb,
  0x1bdb1d7f,0xa0529f12,0x9fdba17f,0x24522311,0x124818b6,0xa1e4a11b,0x96489cb6,0x25e4251b,0xa11ba1e4,0x18b61248,0x251b25e4,0x9cb69648,
  0x9f12a052,0x1d7f1bdb,0x23112452,0xa17f9fdb,0x9bdb9d7f,0x20521f12,0x1fdb217f,0xa452a311,0x924898b6,0x21e4211b,0x16481cb6,0xa5e4a51b,
  0xa7a9a86b,0x1f1218b6,0x2ba72c6a,0xa3119cb6,0xa54da67b,0x242021e4,0x294d2a7a,0xa81fa5e4,0xa1e4a420,0x267b254d,0x25e4281f,0xaa7aa94d,
  0x98b69f12,0x286b27a9,0x1cb62311,0xac6aaba7,0xaa63ab5f,0x21e41bdb,0x2e5f2f59,0xa5e49fdb,0xa86ba967,0x26e024e9,0x2c6a2d65,0xaadea8e8,
  0xa4e9a6e0,0x2967286b,0x28e82ade,0xad65ac6a,0x9bdba1e4,0x2b5f2a63,0x1fdb25e4,0xaf59ae5f,0xac79ad2a,0x24201d7f,0x30743122,0xa81fa17f,
  0xaa31ab91,0x28d026e0,0x2e2d2f8b,0xacceaade,0xa6e0a8d0,0x2b912a31,0x2ade2cce,0xaf8bae2d,0x9d7fa420,0x2d2a2c79,0x217f281f,0xb122b074,
  0xadc2aea7,0x254d1f12,0x31b63294,0xa94da311,0xabf6acde,0x2a31286b,0x2fef30d7,0xae2dac6a,0xa86baa31,0x2cde2bf6,0x2c6a2e2d,0xb0d7afef,
  0x9f12a54d,0x2ea72dc2,0x2311294d,0xb294b1b6,0xaf0cb012,0x267b2052,0x32f73402,0xaa7aa452,0xacdeadf5,0x2b912967,0x30d731e8,0xaf8bad65,
  0xa967ab91,0x2df52cde,0x2d652f8b,0xb1e8b0d7,0xa052a67b,0x30122f0c,0x24522a7a,0xb402b2f7,0xb02cb0d2,0x27a9211b,0x341a34b7,0xaba7a51b,
  0xadc2af0c,0x2c792a63,0x31b632f7,0xb074ae5f,0xaa63ac79,0x2f0c2dc2,0x2e5f3074,0xb2f7b1b6,0xa11ba7a9,0x30d2302c,0x251b2ba7,0xb4b7b41a,
  0xb0d2b194,0x286b21e4,0x34b7356a,0xac6aa5e4,0xaea7b012,0x2d2a2b5f,0x32943402,0xb122af59,0xab5fad2a,0x30122ea7,0x2f593122,0xb402b294,
  0xa1e4a86b,0x319430d2,0x25e42c6a,0xb56ab4b7,0xb17ab257,0x290222ad,0x3552361a,0xad00a6ad,0xaf8cb09f,0x2ddc2c2e,0x33713487,0xb1cfb029,
  0xac2eaddc,0x309f2f8c,0x302931cf,0xb487b371,0xa2ada902,0x3257317a,0x26ad2d00,0xb61ab552,0xb223b31c,0x29992376,0x35eb36c6,0xad97a776,
  0xb039b12d,0x2e8d2cac,0x3426350b,0xb27cb0a6,0xacacae8d,0x312d3039,0x30a6327c,0xb50bb426,0xa376a999,0x331c3223,0x27762d97,0xb6c6b5eb,
  0xb2cdb3e3,0x2a312420,0x3682376f,0xae2da81f,0xb0acb1bb,0x2f3f2d2a,0x3493358d,0xb328b122,0xad2aaf3f,0x31bb30ac,0x31223328,0xb58db493,
  0xa420aa31,0x33e332cd,0x281f2e2d,0xb76fb682,0xb378b456,0x2ac82484,0x3715380a,0xaec3a884,0xb120b24a,0x2ff22da9,0x34ff360e,0xb3d3b19e,
  0xada9aff2,0x324a3120,0x319e33d3,0xb60eb4ff,0xa484aac8,0x34563378,0x28842ec3,0xb80ab715,0xb413b4bc,0x2b5f24e9,0x37a6385a,0xaf59a8e8,
  0xb194b2da,0x30522e28,0x356a368d,0xb43eb219,0xae28b052,0x32da3194,0x3219343e,0xb68db56a,0xa4e9ab5f,0x34bc3413,0x28e82f59,0xb85ab7a6,
  0xb46ab523,0x2bf6254d,0x381a38a8,0xafefa94d,0xb209b36b,0x30ac2ea7,0x35d4370a,0xb493b294,0xaea7b0ac,0x336b3209,0x32943493,0xb70ab5d4,
  0xa54dabf6,0x3523346a,0x294d2fef,0xb8a8b81a,0xb4c3b58c,0x2c4725b2,0x385f38f3,0xb042a9b1,0xb27eb3fd,0x31062f26,0x363c3785,0xb4e7b30f,
  0xaf26b106,0x33fd327e,0x330f34e7,0xb785b63c,0xa5b2ac47,0x358c34c3,0x29b13042,0xb8f3b85f,0xb51cb5f6,0x2c932617,0x38a3393c,0xb08daa16,
  0xb2f4b448,0x31602fa5,0x36a437fe,0xb53ab389,0xafa5b160,0x344832f4,0x3389353a,0xb7feb6a4,0xa617ac93,0x35f6351c,0x2a16308d,0xb93cb8a3,
};
__device__ __align__(128) const uint32_t c_img[2560] = {
  0x326d31ed,0x333b32dd,0x33c33388,0x33fe33ea,0x33c331ed,0x31ed33c3,0xa8b22d64,0xb33bb0c4,0x33ea31ed,0xad64301d,0xb2ddb388,0x315fa8b2,
  0x32dd31ed,0xb3feabc6,0x326dad64,0xad64326d,0x30c431ed,0xaed7b2dd,0x2bc63388,0xa248b3ea,0x2bc631ed,0x315fb3c3,0xb3ea2d64,0x2ed730c4,
  0xa8b231ed,0x3388b01d,0x301db388,0xb1ed28b2,0xb01d31ed,0x22482bc6,0x30c4ad64,0x3388b26d,0x33ea33fe,0x338833c3,0x32dd333b,0x31ed326d,
  0xb2ddb3fe,0xa248b01d,0x326d2ed7,0x338833ea,0x30c433fe,0xb33babc6,0xabc6b33b,0x33fe30c4,0xabc6b3fe,0x31ed32dd,0xb3eaaed7,0x333ba8b2,
  0xa8b233fe,0x2d64b3c3,0xb01d333b,0x315fb26d,0x301db3fe,0xb3fe301d,0x30c42ed7,0x2d64b3ea,0xb26d33fe,0x2ed72bc6,0x33c3b33b,0xa248b0c4,
  0x33c3b3fe,0x315fb2dd,0x28b2aed7,0xaed728b2,0xb0c4b15f,0xaed7b01d,0xabc6ad64,0xa248a8b2,0xabc6b15f,0x315f2bc6,0x33ea3388,0x2ed7326d,
  0x28b2b15f,0x338832dd,0xb01d2d64,0xb1edb3ea,0x301db15f,0x224833c3,0xb0c4b388,0x338830c4,0x326db15f,0xb33b301d,0x33c3ad64,0xb3fe28b2,
  0x33c3b15f,0xb1edabc6,0xa8b23388,0x333bb26d,0x33eab15f,0x2d64b2dd,0xb2dd2d64,0xb15f33ea,0x32ddb15f,0x33feb3c3,0x326db388,0x2d64b0c4,
  0x28b22248,0x2d642bc6,0x301d2ed7,0x315f30c4,0xb01da248,0xb3feb2dd,0xb0c4b33b,0x2d64a8b2,0x326d2248,0x2ed733c3,0xb3c3aed7,0xa248b26d,
  0xb3c3a248,0x315fb01d,0xa8b2333b,0xaed7b3ea,0x33ea2248,0xb388abc6,0x32dd2ed7,0xb1edb0c4,0xb2dda248,0x224832dd,0x326db33b,0xb38828b2,
  0x30c42248,0x333bb3c3,0xabc6aed7,0xb3fe326d,0xabc6a248,0xb1ed301d,0xb3ea333b,0xb33b33ea,0xb26d31ed,0xb33b32dd,0xb3c33388,0xb3fe33ea,
  0xb3c331ed,0xb1ed33c3,0x28b22d64,0x333bb0c4,0xb3ea31ed,0x2d64301d,0x32ddb388,0xb15fa8b2,0xb2dd31ed,0x33feabc6,0xb26dad64,0x2d64326d,
  0xb0c431ed,0x2ed7b2dd,0xabc63388,0x2248b3ea,0xabc631ed,0xb15fb3c3,0x33ea2d64,0xaed730c4,0x28b231ed,0xb388b01d,0xb01db388,0x31ed28b2,
  0x301d31ed,0xa2482bc6,0xb0c4ad64,0xb388b26d,0xb3ea33fe,0xb38833c3,0xb2dd333b,0xb1ed326d,0x32ddb3fe,0x2248b01d,0xb26d2ed7,0xb38833ea,
  0xb0c433fe,0x333babc6,0x2bc6b33b,0xb3fe30c4,0x2bc6b3fe,0xb1ed32dd,0x33eaaed7,0xb33ba8b2,0x28b233fe,0xad64b3c3,0x301d333b,0xb15fb26d,
  0xb01db3fe,0x33fe301d,0xb0c42ed7,0xad64b3ea,0x326d33fe,0xaed72bc6,0xb3c3b33b,0x2248b0c4,0xb3c3b3fe,0xb15fb2dd,0xa8b2aed7,0x2ed728b2,
  0x30c4b15f,0x2ed7b01d,0x2bc6ad64,0x2248a8b2,0x2bc6b15f,0xb15f2bc6,0xb3ea3388,0xaed7326d,0xa8b2b15f,0xb38832dd,0x301d2d64,0x31edb3ea,
  0xb01db15f,0xa24833c3,0x30c4b388,0xb38830c4,0xb26db15f,0x333b301d,0xb3c3ad64,0x33fe28b2,0xb3c3b15f,0x31edabc6,0x28b23388,0xb33bb26d,
  0xb3eab15f,0xad64b2dd,0x32dd2d64,0x315f33ea,0xb2ddb15f,0xb3feb3c3,0xb26db388,0xad64b0c4,0xa8b22248,0xad642bc6,0xb01d2ed7,0xb15f30c4,
  0x301da248,0x33feb2dd,0x30c4b33b,0xad64a8b2,0xb26d2248,0xaed733c3,0x33c3aed7,0x2248b26d,0x33c3a248,0xb15fb01d,0x28b2333b,0x2ed7b3ea,
  0xb3ea2248,0x3388abc6,0xb2dd2ed7,0x31edb0c4,0x32dda248,0xa24832dd,0xb26db33b,0x338828b2,0xb0c42248,0xb33bb3c3,0x2bc6aed7,0x33fe326d,
  0x2bc6a248,0x31ed301d,0x33ea333b,0x333b33ea,0x30c4315f,0x2ed7301d,0x2bc62d64,0x224828b2,0x2bc6315f,0xb15fabc6,0xb3eab388,0xaed7b26d,
  0xa8b2315f,0xb388b2dd,0x301dad64,0x31ed33ea,0xb01d315f,0xa248b3c3,0x30c43388,0xb388b0c4,0xb26d315f,0x333bb01d,0xb3c32d64,0x33fea8b2,
  0xb3c3315f,0x31ed2bc6,0x28b2b388,0xb33b326d,0xb3ea315f,0xad6432dd,0x32ddad64,0x315fb3ea,0xb2dd315f,0xb3fe33c3,0xb26d3388,0xad6430c4,
  0xa8b2a248,0xad64abc6,0xb01daed7,0xb15fb0c4,0x301d2248,0x33fe32dd,0x30c4333b,0xad6428b2,0xb26da248,0xaed7b3c3,0x33c32ed7,0x2248326d,
  0x33c32248,0xb15f301d,0x28b2b33b,0x2ed733ea,0xb3eaa248,0x33882bc6,0xb2ddaed7,0x31ed30c4,0x32dd2248,0xa248b2dd,0xb26d333b,0x3388a8b2,
  0xb0c4a248,0xb33b33c3,0x2bc62ed7,0x33feb26d,0x2bc62248,0x31edb01d,0x33eab33b,0x333bb3ea,0x326d31ed,0x333b32dd,0x33c33388,0x33fe33ea,
  0x33c331ed,0x31ed33c3,0xa8b22d64,0xb33bb0c4,0x33ea31ed,0xad64301d,0xb2ddb388,0x315fa8b2,0x32dd31ed,0xb3feabc6,0x326dad64,0xad64326d,
  0x30c431ed,0xaed7b2dd,0x2bc63388,0xa248b3ea,0x2bc631ed,0x315fb3c3,0xb3ea2d64,0x2ed730c4,0xa8b231ed,0x3388b01d,0x301db388,0xb1ed28b2,
  0xb01d31ed,0x22482bc6,0x30c4ad64,0x3388b26d,0x33ea33fe,0x338833c3,0x32dd333b,0x31ed326d,0xb2ddb3fe,0xa248b01d,0x326d2ed7,0x338833ea,
  0x30c433fe,0xb33babc6,0xabc6b33b,0x33fe30c4,0xabc6b3fe,0x31ed32dd,0xb3eaaed7,0x333ba8b2,0xa8b233fe,0x2d64b3c3,0xb01d333b,0x315fb26d,
  0x301db3fe,0xb3fe301d,0x30c42ed7,0x2d64b3ea,0xb26d33fe,0x2ed72bc6,0x33c3b33b,0xa248b0c4,0x33c3b3fe,0x315fb2dd,0x28b2aed7,0xaed728b2,
  0xb0c4315f,0xaed7301d,0xabc62d64,0xa24828b2,0xabc6315f,0x315fabc6,0x33eab388,0x2ed7b26d,0x28b2315f,0x3388b2dd,0xb01dad64,0xb1ed33ea,
  0x301d315f,0x2248b3c3,0xb0c43388,0x3388b0c4,0x326d315f,0xb33bb01d,0x33c32d64,0xb3fea8b2,0x33c3315f,0xb1ed2bc6,0xa8b2b388,0x333b326d,
  0x33ea315f,0x2d6432dd,0xb2ddad64,0xb15fb3ea,0x32dd315f,0x33fe33c3,0x326d3388,0x2d6430c4,0x28b2a248,0x2d64abc6,0x301daed7,0x315fb0c4,
  0xb01d2248,0xb3fe32dd,0xb0c4333b,0x2d6428b2,0x326da248,0x2ed7b3c3,0xb3c32ed7,0xa248326d,0xb3c32248,0x315f301d,0xa8b2b33b,0xaed733ea,
  0x33eaa248,0xb3882bc6,0x32ddaed7,0xb1ed30c4,0xb2dd2248,0x2248b2dd,0x326d333b,0xb388a8b2,0x30c4a248,0x333b33c3,0xabc62ed7,0xb3feb26d,
  0xabc62248,0xb1edb01d,0xb3eab33b,0xb33bb3ea,0xb26d31ed,0xb33b32dd,0xb3c33388,0xb3fe33ea,0xb3c331ed,0xb1ed33c3,0x28b22d64,0x333bb0c4,
  0xb3ea31ed,0x2d64301d,0x32ddb388,0xb15fa8b2,0xb2dd31ed,0x33feabc6,0xb26dad64,0x2d64326d,0xb0c431ed,0x2ed7b2dd,0xabc63388,0x2248b3ea,
  0xabc631ed,0xb15fb3c3,0x33ea2d64,0xaed730c4,0x28b231ed,0xb388b01d,0xb01db388,0x31ed28b2,0x301d31ed,0xa2482bc6,0xb0c4ad64,0xb388b26d,
  0xb3ea33fe,0xb38833c3,0xb2dd333b,0xb1ed326d,0x32ddb3fe,0x2248b01d,0xb26d2ed7,0xb38833ea,0xb0c433fe,0x333babc6,0x2bc6b33b,0xb3fe30c4,
  0x2bc6b3fe,0xb1ed32dd,0x33eaaed7,0xb33ba8b2,0x28b233fe,0xad64b3c3,0x301d333b,0xb15fb26d,0xb01db3fe,0x33fe301d,0xb0c42ed7,0xad64b3ea,
  0x326d33fe,0xaed72bc6,0xb3c3b33b,0x2248b0c4,0xb3c3b3fe,0xb15fb2dd,0xa8b2aed7,0x2ed728b2,0x29ed29ed,0x29ed29ed,0x29ed29ed,0x29ed29ed,
  0x2bc32a6d,0x2add2bea,0x23c628c4,0xa81da0b2,0x2bc32add,0xa3c6281d,0xabc3aadd,0x23c6a81d,0x29ed2b3b,0xabfea564,0x295fa6d7,0x1a482b88,
  0x25642b88,0xa564ab88,0x25642b88,0xa564ab88,0xa0b22bc3,0x2a6daadd,0xabea23c6,0x28c4281d,0xa8c42bea,0x2a6da0b2,0x28c4abea,0xaa6d20b2,
  0xab3b2bfe,0xa564295f,0x26d79a48,0x2b88a9ed,0x29ed29ed,0x29ed29ed,0x29ed29ed,0x29ed29ed,0xabc3aa6d,0xaaddabea,0xa3c6a8c4,0x281d20b2,
  0x2bc32add,0xa3c6281d,0xabc3aadd,0x23c6a81d,0xa9edab3b,0x2bfe2564,0xa95f26d7,0x9a48ab88,0x25642b88,0xa564ab88,0x25642b88,0xa564ab88,
  0x20b2abc3,0xaa6d2add,0x2beaa3c6,0xa8c4a81d,0xa8c42bea,0x2a6da0b2,0x28c4abea,0xaa6d20b2,0x2b3babfe,0x2564a95f,0xa6d71a48,0xab8829ed,
  0x295f295f,0x295f295f,0x295f295f,0x295f295f,0x23c628c4,0xa81da0b2,0xabc3aa6d,0xaaddabea,0xa3c6281d,0xabc3aadd,0x23c6a81d,0x2bc32add,
  0xa95f26d7,0x9a48ab88,0x29ed2b3b,0xabfea564,0xab882564,0x2b88a564,0xab882564,0x2b88a564,0xabea23c6,0x28c4281d,0x20b2abc3,0xaa6d2add,
  0xaa6d20b2,0xa8c42bea,0x2a6da0b2,0x28c4abea,0xa6d71a48,0xab8829ed,0xab3b2bfe,0xa564295f,0x295f295f,0x295f295f,0x295f295f,0x295f295f,
  0xa3c6a8c4,0x281d20b2,0x2bc32a6d,0x2add2bea,0xa3c6281d,0xabc3aadd,0x23c6a81d,0x2bc32add,0x295fa6d7,0x1a482b88,0xa9edab3b,0x2bfe2564,
  0xab882564,0x2b88a564,0xab882564,0x2b88a564,0x2beaa3c6,0xa8c4a81d,0xa0b22bc3,0x2a6daadd,0xaa6d20b2,0xa8c42bea,0x2a6da0b2,0x28c4abea,
  0x26d79a48,0x2b88a9ed,0x2b3babfe,0x2564a95f,0xabfe2bfe,0xabfe2bfe,0xabfe2bfe,0xabfe2bfe,0xaadd2bea,0xa3c628c4,0x281da0b2,0x2bc3aa6d,
  0xa81d2bc3,0x2adda3c6,0x281dabc3,0xaadd23c6,0x9a482b88,0x29edab3b,0xabfe2564,0x295f26d7,0x26d72b3b,0xa6d7ab3b,0x26d72b3b,0xa6d7ab3b,
  0x2a6d2add,0xabeaa3c6,0x28c4a81d,0x20b22bc3,0x2bea2a6d,0xa0b228c4,0xabeaaa6d,0x20b2a8c4,0x2b8829ed,0x2b3b2bfe,0x2564295f,0xa6d79a48,
  0xabfe2bfe,0xabfe2bfe,0xabfe2bfe,0xabfe2bfe,0x2addabea,0x23c6a8c4,0xa81d20b2,0xabc32a6d,0xa81d2bc3,0x2adda3c6,0x281dabc3,0xaadd23c6,
  0x1a48ab88,0xa9ed2b3b,0x2bfea564,0xa95fa6d7,0x26d72b3b,0xa6d7ab3b,0x26d72b3b,0xa6d7ab3b,0xaa6daadd,0x2bea23c6,0xa8c4281d,0xa0b2abc3,
  0x2bea2a6d,0xa0b228c4,0xabeaaa6d,0x20b2a8c4,0xab88a9ed,0xab3babfe,0xa564a95f,0x26d71a48,0x1a489a48,0x1a489a48,0x1a489a48,0x1a489a48,
  0x281da0b2,0x2bc3aa6d,0x2addabea,0x23c6a8c4,0x2adda3c6,0x281dabc3,0xaadd23c6,0xa81d2bc3,0x2bfea564,0xa95fa6d7,0x9a482b88,0x29edab3b,
  0x2b3ba6d7,0xab3b26d7,0x2b3ba6d7,0xab3b26d7,0x28c4a81d,0x20b22bc3,0xaa6daadd,0x2bea23c6,0x20b2a8c4,0x2bea2a6d,0xa0b228c4,0xabeaaa6d,
  0xa564a95f,0x26d71a48,0x2b8829ed,0x2b3b2bfe,0x1a489a48,0x1a489a48,0x1a489a48,0x1a489a48,0xa81d20b2,0xabc32a6d,0xaadd2bea,0xa3c628c4,
  0x2adda3c6,0x281dabc3,0xaadd23c6,0xa81d2bc3,0xabfe2564,0x295f26d7,0x1a48ab88,0xa9ed2b3b,0x2b3ba6d7,0xab3b26d7,0x2b3ba6d7,0xab3b26d7,
  0xa8c4281d,0xa0b2abc3,0x2a6d2add,0xabeaa3c6,0x20b2a8c4,0x2bea2a6d,0xa0b228c4,0xabeaaa6d,0x2564295f,0xa6d79a48,0xab88a9ed,0xab3babfe,
  0xa95fa95f,0xa95fa95f,0xa95fa95f,0xa95fa95f,0xa3c6a8c4,0x281d20b2,0x2bc32a6d,0x2add2bea,0x23c6a81d,0x2bc32add,0xa3c6281d,0xabc3aadd,
  0x295fa6d7,0x1a482b88,0xa9edab3b,0x2bfe2564,0x2b88a564,0xab882564,0x2b88a564,0xab882564,0x2beaa3c6,0xa8c4a81d,0xa0b22bc3,0x2a6daadd,
  0x2a6da0b2,0x28c4abea,0xaa6d20b2,0xa8c42bea,0x26d79a48,0x2b88a9ed,0x2b3babfe,0x2564a95f,0xa95fa95f,0xa95fa95f,0xa95fa95f,0xa95fa95f,
  0x23c628c4,0xa81da0b2,0xabc3aa6d,0xaaddabea,0x23c6a81d,0x2bc32add,0xa3c6281d,0xabc3aadd,0xa95f26d7,0x9a48ab88,0x29ed2b3b,0xabfea564,
  0x2b88a564,0xab882564,0x2b88a564,0xab882564,0xabea23c6,0x28c4281d,0x20b2abc3,0xaa6d2add,0x2a6da0b2,0x28c4abea,0xaa6d20b2,0xa8c42bea,
  0xa6d71a48,0xab8829ed,0xab3b2bfe,0xa564295f,0x29ed29ed,0x29ed29ed,0x29ed29ed,0x29ed29ed,0x2bc32a6d,0x2add2bea,0x23c628c4,0xa81da0b2,
  0x2bc32add,0xa3c6281d,0xabc3aadd,0x23c6a81d,0x29ed2b3b,0xabfea564,0x295fa6d7,0x1a482b88,0x25642b88,0xa564ab88,0x25642b88,0xa564ab88,
  0xa0b22bc3,0x2a6daadd,0xabea23c6,0x28c4281d,0xa8c42bea,0x2a6da0b2,0x28c4abea,0xaa6d20b2,0xab3b2bfe,0xa564295f,0x26d79a48,0x2b88a9ed,
  0x29ed29ed,0x29ed29ed,0x29ed29ed,0x29ed29ed,0xabc3aa6d,0xaaddabea,0xa3c6a8c4,0x281d20b2,0x2bc32add,0xa3c6281d,0xabc3aadd,0x23c6a81d,
  0xa9edab3b,0x2bfe2564,0xa95f26d7,0x9a48ab88,0x25642b88,0xa564ab88,0x25642b88,0xa564ab88,0x20b2abc3,0xaa6d2add,0x2beaa3c6,0xa8c4a81d,
  0xa8c42bea,0x2a6da0b2,0x28c4abea,0xaa6d20b2,0x2b3babfe,0x2564a95f,0xa6d71a48,0xab8829ed,0x9a481a48,0x9a481a48,0x9a481a48,0x9a481a48,
  0xa81d20b2,0xabc32a6d,0xaadd2bea,0xa3c628c4,0xaadd23c6,0xa81d2bc3,0x2adda3c6,0x281dabc3,0xabfe2564,0x295f26d7,0x1a48ab88,0xa9ed2b3b,
  0xab3b26d7,0x2b3ba6d7,0xab3b26d7,0x2b3ba6d7,0xa8c4281d,0xa0b2abc3,0x2a6d2add,0xabeaa3c6,0xa0b228c4,0xabeaaa6d,0x20b2a8c4,0x2bea2a6d,
  0x2564295f,0xa6d79a48,0xab88a9ed,0xab3babfe,0x9a481a48,0x9a481a48,0x9a481a48,0x9a481a48,0x281da0b2,0x2bc3aa6d,0x2addabea,0x23c6a8c4,
  0xaadd23c6,0xa81d2bc3,0x2adda3c6,0x281dabc3,0x2bfea564,0xa95fa6d7,0x9a482b88,0x29edab3b,0xab3b26d7,0x2b3ba6d7,0xab3b26d7,0x2b3ba6d7,
  0x28c4a81d,0x20b22bc3,0xaa6daadd,0x2bea23c6,0xa0b228c4,0xabeaaa6d,0x20b2a8c4,0x2bea2a6d,0xa564a95f,0x26d71a48,0x2b8829ed,0x2b3b2bfe,
  0xabfe2bfe,0xabfe2bfe,0xabfe2bfe,0xabfe2bfe,0xaadd2bea,0xa3c628c4,0x281da0b2,0x2bc3aa6d,0xa81d2bc3,0x2adda3c6,0x281dabc3,0xaadd23c6,
  0x9a482b88,0x29edab3b,0xabfe2564,0x295f26d7,0x26d72b3b,0xa6d7ab3b,0x26d72b3b,0xa6d7ab3b,0x2a6d2add,0xabeaa3c6,0x28c4a81d,0x20b22bc3,
  0x2bea2a6d,0xa0b228c4,0xabeaaa6d,0x20b2a8c4,0x2b8829ed,0x2b3b2bfe,0x2564295f,0xa6d79a48,0xabfe2bfe,0xabfe2bfe,0xabfe2bfe,0xabfe2bfe,
  0x2addabea,0x23c6a8c4,0xa81d20b2,0xabc32a6d,0xa81d2bc3,0x2adda3c6,0x281dabc3,0xaadd23c6,0x1a48ab88,0xa9ed2b3b,0x2bfea564,0xa95fa6d7,
  0x26d72b3b,0xa6d7ab3b,0x26d72b3b,0xa6d7ab3b,0xaa6daadd,0x2bea23c6,0xa8c4281d,0xa0b2abc3,0x2bea2a6d,0xa0b228c4,0xabeaaa6d,0x20b2a8c4,
  0xab88a9ed,0xab3babfe,0xa564a95f,0x26d71a48,0x3bfb3bff,0x3be53bf2,0x3bbf3bd4,0x3b873ba5,0x3bd03bfb,0x3b013b7c,0x399d3a60,0x378538bc,
  0x35173b52,0xbbc9b7c8,0xb074ba9b,0x3bfe391b,0x319e3b27,0xbbf3b979,0x363cb80a,0x3a2d3bc5,0xba093986,0x3a7eb8f8,0xbae5385f,0x3b3db77a,
  0xbabd393c,0x3bb0b699,0xbc00305b,0x3ba730d7,0xbb2a35c8,0xb8353bb2,0x3a64b1e8,0x3962bbf7,0xba90350b,0xba413bff,0x3602340e,0x3bf6bad8,
  0xac6aa5e4,0xb122af59,0xb402b294,0xb56ab4b7,0xb2deac9c,0xb7bdb5a5,0xb9b3b8d6,0xbb10ba73,0xbb96b676,0xb359bafe,0x3bec3884,0x2a163a29,
  0xbbe0b72c,0x2f27b9d6,0x3b5e3ae8,0xb91633a2,0xb941b9c9,0x38ad3a45,0xb80fbab3,0x36d23b13,0xb850ba0d,0x346f3b4a,0x1fdbbbed,0xb4ab3be8,
  0x3721bb76,0xbace3463,0xb8d13bdd,0x39ebadfb,0x3894bb98,0xb8fd281f,0xbb6a3bbd,0x2e2d3825,0x3b3f3b65,0x3ae83b16,0x3a813ab6,0x3a0d3a49,
  0x3263356a,0xad972b43,0xb5dfb359,0xb8eeb7f3,0xa9b139aa,0xbbedba25,0x3340b889,0x3b983afb,0xbaa2aa16,0xb4cfbb8e,0x3c0038ad,0xb44b38e5,
  0xbb853625,0x3bbdb4c3,0xbbe432ad,0x3bfbaf8b,0xbaacb6d2,0x39243954,0xb65fbace,0x2fbd3bb8,0xb9661648,0xba603bf8,0x383a31cf,0x3b27bbb3,
  0x3219b9eb,0xbb1836f4,0xb9903be5,0x37dd3010,0xb6c6b61a,0xb80ab76f,0xb8a8b85a,0xb93cb8f3,0xbbd7bb87,0xbbf8bbfd,0xbb71bbc9,0xba4dbaf1,
  0xbbfeb9a6,0x305bb91f,0x3bcb3a97,0xb50b37d2,0xb87abbfe,0x3ba13546,0x24523a7e,0xbbb5ba54,0xb576bb63,0x340e3ba3,0xb13bbbd3,0x2c9c3bf2,
  0x386abb3d,0xba2139f8,0x3b57b835,0xbbf13432,0x39e7bc00,0xb8d6adc9,0xbacb3bde,0x372c3457,0x3bdab962,0x3764bb35,0xb9c03122,0xbaf73bef,
  0x398b39cd,0x38fd3946,0x386538b2,0x37853815,0xba85b9c9,0xbb92bb1e,0xbbfebbdd,0xbbc2bbf5,0xb66b3682,0xbb01bb94,0x387fb371,0x3a2d3beb,
  0xbac7bb76,0x3a00ad33,0x36bb3bd4,0xbbeab79b,0xbc0026ad,0x3bf32c38,0xbbd6b109,0x3ba733eb,0x3153bbff,0xb70a3b9e,0x396bba9b,0xbade390c,
  0xb5d4b5bc,0xbbb03b2c,0x32013830,0x3bf6ba67,0x3bccbb52,0x2c06b92e,0xbb83385f,0xb8c73bab,0xb9c5b982,0xba41ba04,0xbab0ba7a,0xbb10bae1,
  0xb8a3b986,0xb52fb74e,0xa94db1e8,0x33d32e91,0xbb54bb4f,0x37bdb523,0x3a9e3bc8,0xb916308d,0x3840b5c8,0x394a3bf9,0xbb42b294,0xb0a6bb0a,
  0x251bbbff,0xaf273bfc,0x327cbbe6,0xb4ab3bc0,0x3be325e4,0xbb2fb4e7,0x39e33884,0xb81aba35,0x3b73bb78,0xb46fb715,0xbbdc3ad1,0x2e2d38cc,
  0x33283676,0x3bfcba19,0x3581bab3,0xba6b3493,0x363136dd,0x34cf3581,0x32c6341a,0x2fbd3153,0xbae1bb65,0xb970ba39,0xb715b889,0xb16cb4f3,
  0xb9a12a7a,0xb924bbfe,0x3a933042,0x37dd3bcc,0x308db9aa,0x3b453b07,0xb94632ad,0xb845bbfa,0xbb68b55e,0x3b1836bb,0xbabab805,0x3a4d38a3,
  0x3bc0b625,0xbbfe2ec3,0x3b9431cf,0xba89b742,0x9cb6b95d,0xbbf8396b,0xb1b63a5c,0x3bb5b840,0x38cc9648,0x3b81bbac,0xac38b85a,0xbbce3933,
  0xbb60bb3a,0xbba1bb83,0xbbd2bbbc,0xbbf1bbe3,0x3815361a,0x39df3907,0x3b2c3a97,0x3be23b9c,0xb9afbbfd,0x3a21294d,0x388e3bee,0xbaf7b328,
  0x3beb39a6,0xb6af37a6,0xba04bbd3,0x3ac42d00,0x360ebb89,0xb7643b42,0x3855baeb,0xb8ee3a85,0x33eb3b63,0x28e8bbf5,0xb5233bde,0x389ebb21,
  0x3c00b9f0,0x2d97b9e3,0xbbdf38db,0xb44b3ac7,0xba673c00,0x358d3487,0x3bfcbab6,0x330fba15,0x3b7a3bf1,0x394a3a93,0x33893764,0xb3d39cb6,
  0x3afb3be2,0x35eb3946,0xb4c328e8,0xbaa9b8cc,0x27763af7,0xbb2fbaba,0x3a76ad97,0x30a63b60,0xaf8b3ac4,0xb994bb94,0x3bf8358d,0xb8743815,
  0xbb4c38ee,0x3bfcb1b6,0xbad5b4cf,0x381a39af,0xbbb3389e,0x3b592c38,0xb76fb970,0xb24b3beb,0xb9d2344b,0xbb923bd2,0xb0f03924,0x3a6bb60e,
  0xb8f3330f,0xbc003b2c,0xb91f3b45,0x323233eb,0xb5b1afbd,0xba00b88e,0xbbc6bb18,0xbbc2bc00,0xb7d2b16c,0xbb6fba04,0xbba3bbfe,0xb86fba67,
  0xbbffb7dd,0x370ab855,0x38b73bf8,0xbbeab631,0xbbf2b845,0x39bcb523,0x2dc93b81,0xbaa5bae1,0xb68dba4d,0xac063bdf,0x382abba1,0xbade39a1,
  0xb457ba89,0xb6543bfc,0x3b16b9df,0xbbd8308d,0x397dbbb5,0xb52fb2c6,0xbbe73a21,0xb8c73b68,0x3a49bbce,0x2311b715,0xba2536af,0xbbd93bc0,
  0xb958b785,0xbb81ba9e,0xbbefbbf3,0xba89bb73,0xbbf7bbc2,0xb9b8bb42,0xaf59b70a,0x384a3328,0xbb8bba2d,0x39dfb27c,0x34263bb0,0xbbceb98b,
  0xb4b7bbea,0x3b6c39e3,0xbafe2c06,0x3185ba85,0xaadebba7,0xb6af3bdc,0x3a58ba41,0xbbe2366b,0x3a29bade,0xbc003581,0x3a45352f,0xb2f7bac7,
  0x3b37bbf6,0x28e8b865,0xbaee37bd,0xbac43c00,0x3b13b8c7,0x3b5cbbfe,0x3463b94a,0xb8993153,0xb9f4bb10,0xb58db87f,0x3029af27,0x389e35d4,
  0x2dfbb3d3,0x399936bb,0x3bf23b2f,0x3ac13bcc,0x3552b916,0x39703bd6,0xbbbab46f,0x330fb9c5,0x3ba530a6,0xb5f7396b,0xb7c8bbfc,0x3be138a3,
  0x3bfdb4ab,0xbb45b201,0x38e038fd,0xb16cbb54,0x391b381a,0xa17fbb83,0xb8f83b92,0x3bcfb840,0x36e82e2d,0x3bfebab0,0x37febb01,0xb845251b,
  0xb77a3a6b,0x3648294d,0x3bb2ba00,0x3a8cbbe3,0xb742b93c,0x2311b340,0x37a6340e,0x3aa93966,0x3b963a4d,0x3b7f3c00,0x380f3a21,0xb0be3219,
  0x3933b50b,0x35eb3be4,0xbbf5b8d6,0x3874b6c6,0x39413bb5,0xbbffb65f,0x38d1b764,0x33ba3bd7,0x3b9c2c9c,0xb994b83a,0x34873ae8,0x324bbbfe,
  0xb7213bf1,0x3b47b990,0xbbbf2d97,0x38c1387a,0x2d00372c,0x3b59b8a8,0x3a39bbed,0xb232b576,0xbbfb3af7,0xb9743b71,0x307434cf,0x3adbb86a,
  0x3b213a0d,0x3c003bcb,0x3b073bbd,0x386f39e7,0x351738ee,0xb599a452,0xbae5b924,0xbbe9bbda,0x3a153b98,0xbb6fb13b,0x2ec3ba60,0x3aa53b3f,
  0xba09344b,0xa884bb57,0x3a643b18,0xbbc3b263,0xb4f33bfb,0x39bcbacb,0xbbac380a,0x3bd8a9b1,0xbb2aafbd,0x36a439c0,0x3402bbf8,0xba6f3aa2,
  0xbbfa3b27,0xb6543a81,0x3907b05b,0x3bd9bb85,0x2c6ab7dd,0xb9da35df,0xbbec3ba1,0xb8203aac,0x3bf53b87,0x3b6c3bec,0x392e3a7e,0x32f73721,
  0xb9e7b785,0xbbfcbb5e,0xba81bbb0,0xb43eb894,0x379b3bfe,0xbc00b80f,0x374eb835,0x38993bfb,0xbb3fba2d,0x3b329fdb,0xb3403a41,0xb8eabbd0,
  0xb90c3b3d,0x3b5cb8d1,0xbbf93122,0x3ac13517,0x29b1bba7,0xb94f3b6a,0x3be4b7bd,0xbaf4b19e,0xbbab3962,0xb9993bbf,0x34e73359,0x3be1ba09,
  0x3b85bbf6,0x353ab99d,0xb83a2f27,0xbbf03abd,0x2e91356a,0xb5f7b074,0xba19b8ad,0xbbcfbb2a,0xb966bb10,0xaba7b63c,0x38a8346f,0x3bb73a90,
  0xbb0aaa16,0xa17fbae5,0x3b1e3ace,0xba8c2c6a,0x36c6b916,0x36ff3c00,0xbbcbb8fd,0x3a50b2de,0xba35b6d2,0x36483a64,0x2d33bbe5,0xb84a3b96,
  0x3bfeb4ab,0xb9fcb602,0x313b3b01,0x37e8bbe0,0x3493b9eb,0xb9b83402,0xbb9e3bc9,0xb1853941,0x35762e2d,0x3b90b9b3,0x3acbbbf3,0x2fefb850,
  0x3a543bcf,0x2884374e,0xb9f8b648,0xbbe9bbab,0x398b3bb7,0xb4db3340,0xbbdcb9fc,0xb911bb85,0xb4323a8c,0xb6a4bbf9,0x3b3539b8,0xbbc3ae91,
  0xb66b3a50,0xad65bbe4,0x38653b90,0xbb0db966,0xbbef384a,0x39da34e7,0x2b43bb6c,0xba6f3b0a,0xbc0037e8,0x3759383a,0x387fbbfc,0xbbf636c6,
  0xb7f33185,0xbb7f3a19,0xbb8e3c00,0xb8203a35,0xb5d42fef,0xba1d38a8,0xbbd63b32,0xbba93bfe,0xb8e5b2f7,0xbbffbb1e,0xb954bb5c,0x30beb493,
  0xb9c5b43e,0xbb9fbbcb,0xb201b94f,0x3a313576,0xbbb8b899,0x3b47ad33,0xb6f43999,0xb3babbf5,0xbb54b8ea,0x3bf9313b,0xbab0353a,0x3790b9e7,
  0xb010bac1,0xb9743b9e,0x3bfdb5f7,0xb8c1b79b,0x251bbaf4,0xbb1b3acb,0x3a9e2ba7,0x2e5fbb3f,0x3af1bbe1,0x3599b92e,0xb546a17f,0xbadb390c,
  0x3b73bbf0,0x3929ba81,0x327cb6ff,0xb49f29b1,0xb825baa9,0x353aaec3,0x3b7c3994,0x3af43bfa,0x360eb0be,0x3bf43a64,0x388e3b47,0xb7372c6a,
  0x38bcb874,0x2ba73bac,0xb979bb59,0x3bf03742,0x3c0033ba,0xbb043402,0x3855b974,0xacce3b96,0x3bc5b24b,0xb6ffb907,0xb6993c00,0x3bb7b933,
  0x363138c1,0x3902bbec,0xbbdf3599,0x34ff3941,0x30d73232,0x39fcb7a6,0x3bffbb6f,0x3a50bb9c,0xb9a13adb,0xb47b380f,0x32c62884,0x3937b721,
  0x3ad8386f,0x3b903bf5,0x35a539bc,0xb7e8ad00,0x3b683be9,0x2ef538d1,0xba93b6a4,0xbb24bbfb,0x3a733aa5,0xbbfcb487,0x39d6b654,0xafef3b21,
  0x1cb63bc3,0xb7b2bbbf,0x3aba39da,0xbbfab517,0xb3a23bd8,0x3b32ba39,0xbb4a2311,0x343e3a15,0xbb603a6f,0x3a3d3074,0x31b6bb7f,0xbb9a3a09,
  0xbbe83bd9,0xb94f3b07,0xa81f35eb,0x38eab4f3,0xb9af3820,0xbbae3ae5,0xbbd23bff,0xba113b2a,0x319e389e,0xb929b426,0xbc00bb45,0xb911bb37,
  0xbbffbac1,0xb805bafe,0x382a217f,0x3bfd3b13,0xbabd330f,0x34dbba58,0x36023bfe,0xbb0db9f4,0xb68dbbe1,0x3a5c3a45,0xbbe7b648,0x3b89adfb,
  0xba90b16c,0x2d653aee,0x39b3bb81,0xbbf63552,0x397dbbcf,0xbbbc3463,0x338939b8,0x39f0bba5,0x32deb845,0xb7593029,0xbb5e39df,0xbba93bfd,
  0x3b7aba8c,0x3beebbf2,0x3a76bb6c,0x36ddb91b,0xbbe0ba89,0xba1dbbba,0x1fdbb6af,0x3a3136e8,0xa776b84a,0x3aeb37c8,0x3ad53c00,0xaa7a377a,
  0xb850bbce,0x3b9f38e0,0xbb6a28e8,0x3790b958,0x3b4cb185,0xb8db38f8,0x30f0bb5c,0x355e3bf7,0x3894bbe2,0xbbf937fe,0x399d358d,0x2e5fbb8b,
  0x39d232f7,0x341abbb2,0xbbc63999,0x395d34b7,0x3bd0bac4,0x3b1bbbef,0x363cb970,0xb49faade,0xb5b13899,0x30422f59,0x38b7b5f7,0x3b3aba29,
  0x3219b3d3,0x3b0438b7,0x3b713bfc,0x34ff397d,0x36e83aa9,0xb8b2adc9,0xbbefbb59,0xb5bcba49,0x3bd730a6,0xb902382a,0xa452bb92,0x39373b7a,
  0xb9583874,0x3371bb16,0x34263c00,0xb982bafb,0x387a381a,0x347bbbe7,0xbb573a00,0x3b242776,0xbb8b324b,0x31093a25,0x3a58bb6f,0xbb4f2f8b,
  0xb86a3a6b,0x2ef53389,0x39c0b70a,0x3bfabb4c,0xaadeb232,0xb83034c3,0xbaee39bc,0xbbff3bb3,0x3bda3bc2,0x37b23a76,0xb5df2c06,0xbb9ab9d2,
  0xbb37b86f,0xba7abbf8,0x3029b654,0x3b7838f3,0x32633bea,0xba3dbad5,0x3c00352f,0xba1135b1,0xb9f4baa5,0x3bc8376f,0xbbba2311,0x39cdb7d2,
  0xbaa23ade,0x3baeb0f0,0xb65fb94a,0xb7373bff,0x3552bbd8,0xbbe6391f,0x38e035eb,0x3682bbf2,0xbaac38c7,0xbbf43bc6,0xb9903b2f,0xacce368d,
  0x3bfdbbd9,0x3ad1bba3,0x37feb994,0x26adb457,0x38a33b9a,0xb8dba452,0xbb83bbae,0x2a7ab86a,0x37423b78,0xbab6b426,0xb907bbe6,0x39aa2ade,
  0xb8403a11,0x341abb57,0x294d3bf4,0xb55ebbda,0xb93339cd,0x3889ba58,0xb7a63ad1,0x3625bb37,0xbbe33737,0x304239c0,0x3b42bb04,0xb95db263,
  0xbb9c3682,0xb2ad3aee,0x3bf5b8b2,0x1648b9f4,0xb3282cce,0xb80535df,0xb9e33902,0xbb3a3aa2,0xad0026ad,0xb1cf3029,0xb4873371,0xb61a3552,
  0xba85b4ff,0xba5cbc00,0x3581b47b,0x3bfd3aac,0xbb21b5bc,0xb85abbba,0x3a393109,0x39a63bfd,0xbac7b937,0x3bbc365f,0xbbfeaef5,0x3b89b219,
  0xba15b982,0x3a9738e0,0xbb07b830,0x3b6336e8,0x3153bb24,0xbbee3990,0x36bb37b2,0x39f0bbd7,0x34f3bb4f,0xbbd337fe,0xaec33a7a,0x3c00b958,
  0x3bccbbfa,0x3aebbb71,0x396bba3d,0x36ddb87a,0x3bfabbff,0x3bdebbef,0x3bacbbc8,0x3b65bb8b,0x3bc03911,0x38303b6a,0xb946ad65,0xbb4fbbd0,
  0x3a353bfd,0xb85f30f0,0xbb1ebbbc,0x35c8b5b1,0x38cc3b0d,0xba7ab99d,0x3b943759,0xbbffb19e,0xb4933b89,0x31e8bbc6,0xad333bee,0xa5e4bbff,
  0xb8153bf6,0x3bc8b63c,0xac38ba1d,0xbb783abd,0xbbf539f0,0x329438b7,0x3b9ebaeb,0xb676b68d,0xbbeb3ba9,0xbbe63c00,0xbb2c3b9f,0xb9cd3a90,
  0xb79b36dd,0xb884382a,0xb92e38db,0xb9c9397d,0x33eb3a31,0xbad1b602,0xba04bbf9,0x3682b2de,0xb90c2a7a,0xbab3bbe7,0x374eb41a,0x3b763b7a,
  0xba673790,0x38b2b9b3,0xb5233b1b,0x26adbbe0,0xbbabb55e,0x3bdd3389,0xbbf9b042,0x3bff2776,0xbae12e5f,0xb3713b5e,0x3bfcb929,0xb5bcb850,
  0xae91b95d,0xbbd43a76,0x34e73805,0x3b52bb4c,0x308db49f,0xb1091fdb,0xb71534db,0xb9823894,0x3b0abb3a,0x3a9bbad5,0x3a19ba5c,0x3986b9d2,
  0x2f8bb7e8,0x3bde3979,0x376f3b32,0xb9aab0d7,0x3bb83b24,0xb1223855,0xbbfdba3d,0xaa16b9a1,0x3bb3afef,0xbab63699,0x391fb94f,0xb6253ad8,
  0x30103bfa,0xb359bbdf,0x35463bae,0xb6d2bb68,0x38f3343e,0x3889bbff,0xbba3353a,0x96483a73,0xbaf13b9a,0x38ad32c6,0x39f8bbf4,0xb9eb9cb6,
  0xb7d238ea,0xb2ad35a5,0x2dc92ba7,0x361ab3a2,0xba543a11,0xbace3a93,0xbb353b04,0xbb873b60,0x3bf23af4,0x31cf39d6,0xbb16b6ff,0xb9a6bbe8,
  0xb4323737,0xbbe5baba,0x2b43b902,0x3bfe39af,0x34573bf0,0xb85abb4a,0x3a2539fc,0xbb63b825,0xbbef2cce,0x3bc9b1b6,0xbb8e347b,0x3b3db60e,
  0xba493bb7,0x3a97a81f,0x34c3bb90,0xbc0038bc,0xb7f3b4ff,0xba7e3bd2,0x39542ef5,0x3962bc00,0xbafb3a50,0xbbd33b7c,0xbbf83bfc,0xbb653bc5,
  0x38e5b937,0x3835b88e,0x36f4b7b2,0x356ab631,0xbb13bbe9,0x31e8b6f4,0x3bf239da,0x36763af1,0x3be83911,0x340e3ab0,0xbb7cb759,0xb72cbb73,
  0x2dfbbbc3,0x32943bfd,0xb7c8bb7f,0x39c93a54,0x38253b0d,0xb8d6ba9e,0x39793a1d,0xba0db98b,0x3ba5ba6f,0xb884b546,0xb8f83bff,0x3b76b432,
  0xb8bc3bf6,0x3ae8b27c,0x3699bb9f,0xbb98366b,0x391bb820,0x3ab3b9f8,0x3bb2bb47,0x3bffbbef,0xbbc53ba9,0xbbed3bdc,0xbbff3bf9,0xbbfb3c00,
  0x377ab0be,0x3bdd3b35,0x2f593974,0xbb52b7f3,0x30d73a31,0xbbbdb865,0xb5a5bb1b,0x3b2735d4,0x3bf733ba,0xbbd42b43,0x3afeb599,0xb98638e5,
  0xbad83790,0x3a60b87f,0xb9d63929,0x393cb9c5,0x34b738c1,0x3a9bbb8e,0xba45a884,0xb5c83bb8,0xba732e5f,0xb80a3bd6,0x3b4ab4db,0x350bbb54,
  0xba293adb,0xb85f3954,0xb46336a4,0x25e43010,0x33a2b49f,0x305bb201,0x281fad65,0xac9c251b,0x3f803f80,0x3f803f80,0x3f803f80,0x3f803f80,
  0x3f803f80,0x3f803f80,0x3f803f80,0x3f803f80,0x3f803f80,0x3f803f80,0x3f803f80,0x3f803f80,0x3f803f80,0x3f803f80,0x3f803f80,0x3f803f80,
  0x3f803f80,0x3f803f80,0x3f803f80,0x3f803f80,0x3f803f80,0x3f803f80,0x3f803f80,0x3f803f80,0x3f803f80,0x3f803f80,0x3f803f80,0x3f803f80,
  0x3f803f80,0x3f803f80,0x3f803f80,0x3f803f80,0x3f803f80,0x3f803f80,0x3f803f80,0x3f803f80,0x3f803f80,0x3f803f80,0x3f803f80,0x3f803f80,
  0x3f803f80,0x3f803f80,0x3f803f80,0x3f803f80,0x3f803f80,0x3f803f80,0x3f803f80,0x3f803f80,0x3f803f80,0x3f803f80,0x3f803f80,0x3f803f80,
  0x3f803f80,0x3f803f80,0x3f803f80,0x3f803f80,0x3f803f80,0x3f803f80,0x3f803f80,0x3f803f80,0x3f803f80,0x3f803f80,0x3f803f80,0x3f803f80,
  0x3f803f80,0x3f803f80,0x3f803f80,0x3f803f80,0x3f803f80,0x3f803f80,0x3f803f80,0x3f803f80,0x3f803f80,0x3f803f80,0x3f803f80,0x3f803f80,
  0x3f803f80,0x3f803f80,0x3f803f80,0x3f803f80,0x3f803f80,0x3f803f80,0x3f803f80,0x3f803f80,0x3f803f80,0x3f803f80,0x3f803f80,0x3f803f80,
  0x3f803f80,0x3f803f80,0x3f803f80,0x3f803f80,0x3f803f80,0x3f803f80,0x3f803f80,0x3f803f80,0x3f803f80,0x3f803f80,0x3f803f80,0x3f803f80,
  0x3f803f80,0x3f803f80,0x3f803f80,0x3f803f80,0x3f803f80,0x3f803f80,0x3f803f80,0x3f803f80,0x3f803f80,0x3f803f80,0x3f803f80,0x3f803f80,
  0x3f803f80,0x3f803f80,0x3f803f80,0x3f803f80,0x3f803f80,0x3f803f80,0x3f803f80,0x3f803f80,0x3f803f80,0x3f803f80,0x3f803f80,0x3f803f80,
  0x3f803f80,0x3f803f80,0x3f803f80,0x3f803f80,0x3f803f80,0x3f803f80,0x3f803f80,0x3f803f80,0x3f803f80,0x3f803f80,0x3f803f80,0x3f803f80,
  0x3f803f80,0x3f803f80,0x3f803f80,0x3f803f80,0x3f803f80,0x3f803f80,0x3f803f80,0x3f803f80,0x3f803f80,0x3f803f80,0x3f803f80,0x3f803f80,
  0x3f803f80,0x3f803f80,0x3f803f80,0x3f803f80,0x3f803f80,0x3f803f80,0x3f803f80,0x3f803f80,0x3f803f80,0x3f803f80,0x3f803f80,0x3f803f80,
  0x3f803f80,0x3f803f80,0x3f803f80,0x3f803f80,0x3f803f80,0x3f803f80,0x3f803f80,0x3f803f80,0x3f803f80,0x3f803f80,0x3f803f80,0x3f803f80,
  0x3f803f80,0x3f803f80,0x3f803f80,0x3f803f80,0x3f803f80,0x3f803f80,0x3f803f80,0x3f803f80,0x3f803f80,0x3f803f80,0x3f803f80,0x3f803f80,
  0x3f803f80,0x3f803f80,0x3f803f80,0x3f803f80,0x3f803f80,0x3f803f80,0x3f803f80,0x3f803f80,0x3f803f80,0x3f803f80,0x3f803f80,0x3f803f80,
  0x3f803f80,0x3f803f80,0x3f803f80,0x3f803f80,0x3f803f80,0x3f803f80,0x3f803f80,0x3f803f80,0x3f803f80,0x3f803f80,0x3f803f80,0x3f803f80,
  0x3f803f80,0x3f803f80,0x3f803f80,0x3f803f80,0x3f803f80,0x3f803f80,0x3f803f80,0x3f803f80,0x3f803f80,0x3f803f80,0x3f803f80,0x3f803f80,
  0x3f803f80,0x3f803f80,0x3f803f80,0x3f803f80,0x3f803f80,0x3f803f80,0x3f803f80,0x3f803f80,0x3f803f80,0x3f803f80,0x3f803f80,0x3f803f80,
  0x3f803f80,0x3f803f80,0x3f803f80,0x3f803f80,0x3f803f80,0x3f803f80,0x3f803f80,0x3f803f80,0x3f803f80,0x3f803f80,0x3f803f80,0x3f803f80,
  0x3f803f80,0x3f803f80,0x3f803f80,0x3f803f80,0x3f803f80,0x3f803f80,0x3f803f80,0x3f803f80,0x3f803f80,0x3f803f80,0x3f803f80,0x3f803f80,
  0x3f803f80,0x3f803f80,0x3f803f80,0x3f803f80,0x3f803f80,0x3f803f80,0x3f803f80,0x3f803f80,0x3f803f80,0x3f803f80,0x3f803f80,0x3f803f80,
  0x3f803f80,0x3f803f80,0x3f803f80,0x3f803f80,0x3f803f80,0x3f803f80,0x3f803f80,0x3f803f80,0x3f803f80,0x3f803f80,0x3f803f80,0x3f803f80,
  0x3f803f80,0x3f803f80,0x3f803f80,0x3f803f80,0x3f803f80,0x3f803f80,0x3f803f80,0x3f803f80,0x3f803f80,0x3f803f80,0x3f803f80,0x3f803f80,
  0x3f803f80,0x3f803f80,0x3f803f80,0x3f803f80,0x3f803f80,0x3f803f80,0x3f803f80,0x3f803f80,0x3f803f80,0x3f803f80,0x3f803f80,0x3f803f80,
  0x3f803f80,0x3f803f80,0x3f803f80,0x3f803f80,0x3f803f80,0x3f803f80,0x3f803f80,0x3f803f80,0x3f803f80,0x3f803f80,0x3f803f80,0x3f803f80,
  0x3f803f80,0x3f803f80,0x3f803f80,0x3f803f80,0x3f803f80,0x3f803f80,0x3f803f80,0x3f803f80,0x3f803f80,0x3f803f80,0x3f803f80,0x3f803f80,
  0x3f803f80,0x3f803f80,0x3f803f80,0x3f803f80,0x3f803f80,0x3f803f80,0x3f803f80,0x3f803f80,0x3f803f80,0x3f803f80,0x3f803f80,0x3f803f80,
  0x3f803f80,0x3f803f80,0x3f803f80,0x3f803f80,0x3f803f80,0x3f803f80,0x3f803f80,0x3f803f80,0x3f803f80,0x3f803f80,0x3f803f80,0x3f803f80,
  0x3f803f80,0x3f803f80,0x3f803f80,0x3f803f80,0x3f803f80,0x3f803f80,0x3f803f80,0x3f803f80,0x3f803f80,0x3f803f80,0x3f803f80,0x3f803f80,
  0x3f803f80,0x3f803f80,0x3f803f80,0x3f803f80,0x3f803f80,0x3f803f80,0x3f803f80,0x3f803f80,0x3f803f80,0x3f803f80,0x3f803f80,0x3f803f80,
  0x3f803f80,0x3f803f80,0x3f803f80,0x3f803f80,0x3f803f80,0x3f803f80,0x3f803f80,0x3f803f80,0x3f803f80,0x3f803f80,0x3f803f80,0x3f803f80,
  0x3f803f80,0x3f803f80,0x3f803f80,0x3f803f80,0x3f803f80,0x3f803f80,0x3f803f80,0x3f803f80,0x3f803f80,0x3f803f80,0x3f803f80,0x3f803f80,
  0x3f803f80,0x3f803f80,0x3f803f80,0x3f803f80,0x3f803f80,0x3f803f80,0x3f803f80,0x3f803f80,0x3f803f80,0x3f803f80,0x3f803f80,0x3f803f80,
  0x3f803f80,0x3f803f80,0x3f803f80,0x3f803f80,0x3f803f80,0x3f803f80,0x3f803f80,0x3f803f80,0x3f803f80,0x3f803f80,0x3f803f80,0x3f803f80,
  0x3f803f80,0x3f803f80,0x3f803f80,0x3f803f80,0x3f803f80,0x3f803f80,0x3f803f80,0x3f803f80,0x3f803f80,0x3f803f80,0x3f803f80,0x3f803f80,
  0x3f803f80,0x3f803f80,0x3f803f80,0x3f803f80,0x3f803f80,0x3f803f80,0x3f803f80,0x3f803f80,0x3f803f80,0x3f803f80,0x3f803f80,0x3f803f80,
  0x3f803f80,0x3f803f80,0x3f803f80,0x3f803f80,0x3f803f80,0x3f803f80,0x3f803f80,0x3f803f80,0x3f803f80,0x3f803f80,0x3f803f80,0x3f803f80,
  0x3f803f80,0x3f803f80,0x3f803f80,0x3f803f80,0x3f803f80,0x3f803f80,0x3f803f80,0x3f803f80,0x3f803f80,0x3f803f80,0x3f803f80,0x3f803f80,
  0x3f803f80,0x3f803f80,0x3f803f80,0x3f803f80,0x3f803f80,0x3f803f80,0x3f803f80,0x3f803f80,0x3f803f80,0x3f803f80,0x3f803f80,0x3f803f80,
  0x3f803f80,0x3f803f80,0x3f803f80,0x3f803f80,0x3f803f80,0x3f803f80,0x3f803f80,0x3f803f80,0x3f803f80,0x3f803f80,0x3f803f80,0x3f803f80,
  0x3f803f80,0x3f803f80,0x3f803f80,0x3f803f80,0x3f803f80,0x3f803f80,0x3f803f80,0x3f803f80,0x3f803f80,0x3f803f80,0x3f803f80,0x3f803f80,
  0x3f803f80,0x3f803f80,0x3f803f80,0x3f803f80,
};

__device__ __align__(128) float    g_part[16][8][2176];
__device__ __align__(128) float    g_kv[16][2176];
__device__ __align__(128) uint4    g_o[16 * 16 * 1024];
__device__ __align__(128) unsigned g_ocnt[2 * 16 * 32];
__device__ unsigned g_epoch[128];
#define GSTAMP(role, i) do {} while (0)
#define STAMP(role, i) do {} while (0)
#define PDUMP(role) do {} while (0)
#define PROF_SMEM 0

constexpr int STAGE_BYTES = 57344;
constexpr int OFF_H = 4 * 16384, OFF_VP = 9 * 16384, OFF_SPARE = 10 * 16384;
constexpr int OFF_XT = 172032, XT_STRIDE = 4112;
constexpr int OFF_BAR = 204928, OFF_EPOCH = OFF_BAR + 640, OFF_EX = OFF_BAR + 656, OFF_D = OFF_BAR + 672, OFF_SCALE = OFF_BAR + 704;
constexpr int OFF_F2F = 205824, OFF_F2I = 207872, OFF_F4 = 209920, OFF_ONES = 214016, OFF_KVB = 214016;
constexpr int OFF_STG = 219136, STG_STRIDE = 4352, SMEM_TOTAL = 232192 + PROF_SMEM;
enum { B_FULL1 = 0, B_EMPTY1 = 3, B_Q = 6, B_ODONE1 = 7, B_O1RDY = 8, B_H = 9, B_XRAW = 10, B_XT = 11, B_KV = 12, B_Y = 13,  B_AFREE = 15,
       B_STG = 18, B_ODONE = 24, B_XFREE = 25, B_FULL2 = 33, B_CONS2 = 49, B_SFREE = 14, B_PKRDY = 62, B_PKFREE = 64, B_H2 = 65, B_G1DONE = 66, B_COUNT = 67, B_FIRST = 67 };
constexpr uint64_t SLOT_A = 0x6859468594685948ull, SLOT_B = 0x7103271032710326ull;
constexpr int NPRE = 6, BEARLY = 3;
__host__ __device__ constexpr int bar_count(int i) {
  return i < B_EMPTY1 ? 1 : i < B_Q ? 4 : i == B_XT ? 4 : i == B_H ? 4 : (i == B_SFREE || i == B_G1DONE) ? 2 : i >= B_PKFREE ? 4 : i >= B_PKRDY ? 8 : i == B_KV ? 2 : i == B_Y ? 9
       : (i >= B_AFREE && i < B_STG) ? 16 : (i == B_ODONE || i == B_ODONE1) ? 8 : (i >= B_XFREE && i < B_FULL2) ? 4
       : i >= B_CONS2 ? 4 : (i >= B_FULL2 && i < B_FULL2 + NPRE) ? 2 : 1;
}
__host__ __device__ constexpr uint64_t bar_counts(int r) {
  uint64_t v = 0;
  for (int w = 0; w < 11; w++) v |= (uint64_t)(bar_count(1 + 11 * r + w) - 1) << (4 * w);
  return v;
}
constexpr uint32_t SW128 = 64 | (1u << 30);
constexpr int SPIN_LIMIT = 1 << 22;
#define SPLIT0 2
#define PFD 3
#define PD1 700
#define PD2 450
#define QPF 6
#define BPACE 250
#define OCH 3
#define O1D 1
#define HOLD2 12
#define D1 100
#define TRICK 3
#define HSTART 1500
#define PACE 800

__device__ __forceinline__ uint32_t smem_u32(const void* p) { return (uint32_t)__cvta_generic_to_shared(p); }
__device__ __forceinline__ void wg_fence() { asm volatile("wgmma.fence.sync.aligned;" ::: "memory"); }
__device__ __forceinline__ void wg_commit() { asm volatile("wgmma.commit_group.sync.aligned;" ::: "memory"); }
template <int N> __device__ __forceinline__ void wg_wait() { asm volatile("wgmma.wait_group.sync.aligned %0;" ::"n"(N) : "memory"); }
template <int N> __device__ __forceinline__ void keep(float (&d)[N]) {
#pragma unroll
  for (int i = 0; i < N; i++) asm volatile("" : "+f"(d[i])::"memory");
}
__device__ __forceinline__ void mbar_init(uint32_t bar, int cnt) { asm volatile("mbarrier.init.shared::cta.b64 [%0], %1;" ::"r"(bar), "r"(cnt)); }
__device__ __forceinline__ void mbar_expect(uint32_t bar, int bytes) { asm volatile("mbarrier.arrive.expect_tx.shared::cta.b64 _, [%0], %1;" ::"r"(bar), "r"(bytes) : "memory"); }
__device__ __forceinline__ void mbar_arrive(uint32_t bar) { asm volatile("mbarrier.arrive.shared::cta.b64 _, [%0];" ::"r"(bar) : "memory"); }
__device__ __forceinline__ void mbar_arrive_cl(uint32_t bar, uint32_t cta) {
  asm volatile("{\n.reg .b32 r;\nmapa.shared::cluster.u32 r, %0, %1;\nmbarrier.arrive.shared::cluster.b64 _, [r];\n}\n" ::"r"(bar), "r"(cta) : "memory");
}
__device__ __forceinline__ void mbar_wait(uint32_t bar, uint32_t parity) {
  asm volatile("{\n.reg .pred p;\n.reg .u32 n;\nmov.u32 n, 0;\n"
               "W_%=:\nmbarrier.try_wait.parity.shared::cta.b64 p, [%0], %1;\n@p bra D_%=;\n"
               "add.u32 n, n, 1;\nsetp.lt.u32 p, n, %2;\n@p bra W_%=;\ntrap;\nD_%=:\n}\n" ::"r"(bar), "r"(parity), "n"(SPIN_LIMIT) : "memory");
}
__device__ __forceinline__ void fence_async() { asm volatile("fence.proxy.async.shared::cta;" ::: "memory"); }
__device__ __forceinline__ void bar_sync(int id) { asm volatile("bar.sync %0, 128;" ::"r"(id) : "memory"); }
__device__ __forceinline__ void tma2d(uint32_t dst, const CUtensorMap* m, int c0, int c1, uint32_t bar) {
  asm volatile("cp.async.bulk.tensor.2d.shared::cluster.global.mbarrier::complete_tx::bytes [%0], [%1, {%3, %4}], [%2];"
               ::"r"(dst), "l"(m), "r"(bar), "r"(c0), "r"(c1) : "memory");
}
__device__ __forceinline__ void tma2d_mc(uint32_t dst, const CUtensorMap* m, int c0, int c1, uint32_t bar) {
  asm volatile("cp.async.bulk.tensor.2d.shared::cluster.global.mbarrier::complete_tx::bytes.multicast::cluster [%0], [%1, {%3, %4}], [%2], %5;"
               ::"r"(dst), "l"(m), "r"(bar), "r"(c0), "r"(c1), "h"((uint16_t)3) : "memory");
}
__device__ __forceinline__ void tma3d(uint32_t dst, const CUtensorMap* m, int c0, int c1, int c2, uint32_t bar) {
  asm volatile("cp.async.bulk.tensor.3d.shared::cluster.global.mbarrier::complete_tx::bytes [%0], [%1, {%3, %4, %5}], [%2];"
               ::"r"(dst), "l"(m), "r"(bar), "r"(c0), "r"(c1), "r"(c2) : "memory");
}
__device__ __forceinline__ void tma4d(uint32_t dst, const CUtensorMap* m, int c0, int c1, int c2, int c3, uint32_t bar) {
  asm volatile("cp.async.bulk.tensor.4d.shared::cluster.global.mbarrier::complete_tx::bytes [%0], [%1, {%3, %4, %5, %6}], [%2];"
               ::"r"(dst), "l"(m), "r"(bar), "r"(c0), "r"(c1), "r"(c2), "r"(c3) : "memory");
}
__device__ __forceinline__ void bulk_ld(uint32_t dst, const void* src, int bytes, uint32_t bar) {
  asm volatile("cp.async.bulk.shared::cluster.global.mbarrier::complete_tx::bytes [%0], [%1], %2, [%3];" ::"r"(dst), "l"(src), "r"(bytes), "r"(bar) : "memory");
}
__device__ __forceinline__ void bulk_ld_mc(uint32_t dst, const void* src, int bytes, uint32_t bar) {
  asm volatile("cp.async.bulk.shared::cluster.global.mbarrier::complete_tx::bytes.multicast::cluster [%0], [%1], %2, [%3], %4;"
               ::"r"(dst), "l"(src), "r"(bytes), "r"(bar), "h"((uint16_t)3) : "memory");
}
__device__ __forceinline__ void tma2d_st(const CUtensorMap* m, uint32_t src, int c0, int c1) {
  asm volatile("cp.async.bulk.tensor.2d.global.shared::cta.bulk_group [%0, {%2, %3}], [%1];" ::"l"(m), "r"(src), "r"(c0), "r"(c1) : "memory");
}
__device__ __forceinline__ void ldsm4(uint32_t (&r)[4], uint32_t a) {
  asm volatile("ldmatrix.sync.aligned.m8n8.x4.shared.b16 {%0,%1,%2,%3}, [%4];" : "=r"(r[0]), "=r"(r[1]), "=r"(r[2]), "=r"(r[3]) : "r"(a) : "memory");
}
__device__ __forceinline__ void ldsm4t(uint32_t (&r)[4], uint32_t a) {
  asm volatile("ldmatrix.sync.aligned.m8n8.x4.trans.shared.b16 {%0,%1,%2,%3}, [%4];" : "=r"(r[0]), "=r"(r[1]), "=r"(r[2]), "=r"(r[3]) : "r"(a) : "memory");
}
__device__ __forceinline__ void stsm4(uint32_t a, uint32_t r0, uint32_t r1, uint32_t r2, uint32_t r3) {
  asm volatile("stmatrix.sync.aligned.m8n8.x4.shared.b16 [%0], {%1,%2,%3,%4};" ::"r"(a), "r"(r0), "r"(r1), "r"(r2), "r"(r3) : "memory");
}
__device__ __forceinline__ uint32_t pk2(float lo, float hi) { uint32_t r; asm("cvt.rn.bf16x2.f32 %0, %1, %2;" : "=r"(r) : "f"(hi), "f"(lo)); return r; }
__device__ __forceinline__ uint32_t hmul(uint32_t a, uint32_t b) { uint32_t r; asm("mul.rn.bf16x2 %0, %1, %2;" : "=r"(r) : "r"(a), "r"(b)); return r; }
__device__ __forceinline__ uint32_t hadd(uint32_t a, uint32_t b) { uint32_t r; asm("add.rn.bf16x2 %0, %1, %2;" : "=r"(r) : "r"(a), "r"(b)); return r; }
__device__ __forceinline__ uint32_t hmin(uint32_t a, uint32_t b) { uint32_t r; asm("min.bf16x2 %0, %1, %2;" : "=r"(r) : "r"(a), "r"(b)); return r; }
__device__ __forceinline__ uint32_t hmaxabs(uint32_t a, uint32_t b) { uint32_t r; asm("max.xorsign.abs.bf16x2 %0, %1, %2;" : "=r"(r) : "r"(a), "r"(b)); return r; }
__device__ __forceinline__ float ex2(float x) { float r; asm("ex2.approx.ftz.f32 %0, %1;" : "=f"(r) : "f"(x)); return r; }
__device__ __forceinline__ float rcp_fast(float x) { float r; asm("rcp.approx.ftz.f32 %0, %1;" : "=f"(r) : "f"(x)); return r; }
__device__ __forceinline__ uint32_t phi2(float lo, float hi) {
  uint32_t t;
  asm("cvt.rn.relu.bf16x2.f32 %0, %1, %2;" : "=r"(t) : "f"(hi), "f"(lo));
  const uint32_t e = pk2(ex2(lo * 1.4426950408889634f), ex2(hi * 1.4426950408889634f));
  return hadd(hadd(t, hmin(e, 0x3F803F80u)), 0x35863586u);
}
__device__ __forceinline__ bool opaque_true() { uint32_t v; asm volatile("mov.u32 %0, %%nctaid.y;" : "=r"(v)); return v != 0; }
__device__ __forceinline__ int norm_exp(uint32_t (&v)[32], float f0) {
  uint32_t m[4] = {hmaxabs(__float_as_uint(f0) >> 16, v[0]), v[1], v[2], v[3]};
#pragma unroll
  for (int i = 4; i < 32; i++) m[i & 3] = hmaxabs(m[i & 3], v[i]);
  m[0] = hmaxabs(hmaxabs(m[0], m[1]), hmaxabs(m[2], m[3]));
  const int e = min(max((int)(__reduce_max_sync(~0u, max(m[0] & 0x7FFFu, (m[0] >> 16) & 0x7FFFu)) >> 7), 1), 253);
  if (e > 141) {
#pragma unroll
    for (int i = 0; i < 32; i++) v[i] = hmul(v[i], 0x07000700u);
  }
  return e;
}
__device__ __forceinline__ void norm_cvt(uint32_t (&v)[32], float f0, int e) {
  const uint32_t sc = (e > 141 ? 255 - e : 142 - e) * 0x00800080u;
#pragma unroll
  for (int i = 0; i < 32; i++) {
    const uint32_t a = hmul(v[i], sc);
    v[i] = (a & 0x0FFF0FFFu) * 7 + a;
  }
  v[0] = __byte_perm(v[0], __half_as_ushort(__float2half_rn(f0 * __uint_as_float((254 - e) << 23))), 0x3254);
}
__device__ __forceinline__ void poll_ge(const unsigned* p, unsigned target) {
#pragma unroll 1
  for (int n = 0; n < SPIN_LIMIT; n++) {
    unsigned v;
    asm volatile("ld.relaxed.gpu.global.u32 %0, [%1];" : "=r"(v) : "l"(p) : "memory");
    if (__all_sync(~0u, (int)(v - target) >= 0)) { asm volatile("fence.acquire.gpu;" ::: "memory"); return; }
  }
  __trap();
}

__device__ __forceinline__ bool elect_one() {
  uint32_t p;
  asm volatile("{\n.reg .pred p;\nelect.sync _|p, 0xffffffff;\nselp.u32 %0, 1, 0, p;\n}\n" : "=r"(p));
  return p;
}
__device__ __forceinline__ uint4 ld_na4(const void* p) {
  uint4 v;
  asm volatile("ld.global.L1::no_allocate.v4.u32 {%0,%1,%2,%3}, [%4];" : "=r"(v.x), "=r"(v.y), "=r"(v.z), "=r"(v.w) : "l"(p) : "memory");
  return v;
}
__device__ __forceinline__ void st_cg4(void* p, uint4 v) {
  asm volatile("st.global.cg.v4.u32 [%0], {%1,%2,%3,%4};" ::"l"(p), "r"(v.x), "r"(v.y), "r"(v.z), "r"(v.w) : "memory");
}
__device__ __forceinline__ uint32_t mapa(uint32_t a, uint32_t cta) { uint32_t r; asm("mapa.shared::cluster.u32 %0, %1, %2;" : "=r"(r) : "r"(a), "r"(cta)); return r; }
__device__ __forceinline__ void st_async(uint32_t a, uint32_t v, uint32_t bar) {
  asm volatile("st.async.weak.shared::cluster.mbarrier::complete_tx::bytes.b32 [%0], %1, [%2];" ::"r"(a), "r"(v), "r"(bar) : "memory");
}
__device__ __forceinline__ void st_async4(uint32_t a, uint32_t x, uint32_t y, uint32_t z, uint32_t w, uint32_t bar) {
  asm volatile("st.async.weak.shared::cluster.mbarrier::complete_tx::bytes.v4.b32 [%0], {%1,%2,%3,%4}, [%5];" ::"r"(a), "r"(x), "r"(y), "r"(z), "r"(w), "r"(bar) : "memory");
}
__device__ __forceinline__ void tma3d_st(const CUtensorMap* m, uint32_t src, int c0, int c1, int c2) {
  asm volatile("cp.async.bulk.tensor.3d.global.shared::cta.bulk_group [%0, {%2, %3, %4}], [%1];" ::"l"(m), "r"(src), "r"(c0), "r"(c1), "r"(c2) : "memory");
}
__device__ __forceinline__ uint4 ld_rlx4(const void* p) {
  uint4 v;
  asm volatile("{\n.reg .b128 t;\n.reg .b64 a, b;\nld.relaxed.gpu.global.b128 t, [%4];\nmov.b128 {a, b}, t;\nmov.b64 {%0, %1}, a;\nmov.b64 {%2, %3}, b;\n}\n"
               : "=r"(v.x), "=r"(v.y), "=r"(v.z), "=r"(v.w) : "l"(p) : "memory");
  return v;
}
__device__ __forceinline__ void ld_stale4(uint4& v, const void* p, uint32_t tag) {
  asm volatile("{\n.reg .b128 t;\n.reg .b64 a, b;\n.reg .b32 x;\n.reg .pred p;\n"
               "lop3.b32 x, %0, %5, 1, 0x28;\nsetp.ne.u32 p, x, 0;\n"
               "mov.b64 a, {%0, %1};\nmov.b64 b, {%2, %3};\nmov.b128 t, {a, b};\n"
               "@p ld.relaxed.gpu.global.b128 t, [%4];\n"
               "mov.b128 {a, b}, t;\nmov.b64 {%0, %1}, a;\nmov.b64 {%2, %3}, b;\n}\n"
               : "+r"(v.x), "+r"(v.y), "+r"(v.z), "+r"(v.w) : "l"(p), "r"(tag) : "memory");
}
__device__ __forceinline__ void st_tag4(void* p, float a, float b, float c, float d, uint32_t tag) {
  asm volatile("{\n.reg .b128 t;\n.reg .b64 a, b;\nmov.b64 a, {%1, %2};\nmov.b64 b, {%3, %4};\nmov.b128 t, {a, b};\nst.relaxed.gpu.global.b128 [%0], t;\n}\n"
               ::"l"(p), "r"((__float_as_uint(a) & ~1u) | tag), "f"(b), "f"(c), "f"(d) : "memory");
}
__device__ __forceinline__ uint32_t stale8(const uint4 (&f)[8], uint32_t tag) {
  uint32_t r[4];
#pragma unroll
  for (int i = 0; i < 4; i++) asm("lop3.b32 %0, %1, %2, %3, 0x7E;" : "=r"(r[i]) : "r"(f[2 * i].x), "r"(f[2 * i + 1].x), "r"(tag));
  asm("lop3.b32 %0, %0, %1, %2, 0xFE;" : "+r"(r[0]) : "r"(r[1]), "r"(r[2]));
  return r[0] | r[3];
}

struct ConvC { uint32_t a1[2][4], wa[2], wb[2], sg; };
__device__ __forceinline__ uint64_t dsc(uint32_t lo, uint32_t hi) { return ((uint64_t)hi << 32) | lo; }
__device__ __forceinline__ uint32_t hfma(uint32_t a, uint32_t b, uint32_t c) { uint32_t r; asm("fma.rn.f16x2 %0, %1, %2, %3;" : "=r"(r) : "r"(a), "r"(b), "r"(c)); return r; }
__device__ __forceinline__ uint32_t hfnma(uint32_t a, uint32_t b, uint32_t c) { uint32_t r; asm("{.reg .b32 n; neg.f16x2 n, %1; fma.rn.f16x2 %0, n, %2, %3;}" : "=r"(r) : "r"(a), "r"(b), "r"(c)); return r; }
__device__ __forceinline__ uint32_t hmul16(uint32_t a, uint32_t b) { uint32_t r; asm("mul.rn.f16x2 %0, %1, %2;" : "=r"(r) : "r"(a), "r"(b)); return r; }
template <int N> __device__ __forceinline__ void keepu(uint32_t (&d)[N]) {
#pragma unroll
  for (int i = 0; i < N; i++) asm volatile("" : "+r"(d[i])::"memory");
}
__device__ __forceinline__ void conv_m1(const ConvC& K, uint32_t (&u)[16], uint32_t l) {
  wg_fence();
  wgmma_hrs_n64<1>(u, K.a1[0][0], K.a1[0][1], K.a1[0][2], K.a1[0][3], dsc(l, 32), 0);
  wgmma_hrs_n64<1>(u, K.a1[1][0], K.a1[1][1], K.a1[1][2], K.a1[1][3], dsc(l + 16, 32), 1);
  wg_commit();
}
__device__ __forceinline__ void conv_s2(const ConvC& K, uint32_t (&u)[16], uint32_t (&Z)[2][8], uint32_t dfl) {
  uint32_t fr[8], fi[8];
#pragma unroll
  for (int c = 0; c < 8; c++) {
    const uint32_t r = hfma(K.wa[c & 1], u[2 * c + 1], u[2 * c]);
    fi[c] = hfma(K.wb[c & 1], r, u[2 * c + 1]);
    fr[c] = hfma(K.wa[c & 1], fi[c], r);
  }
  wg_fence();
#pragma unroll
  for (int p = 0; p < 2; p++) {
    wgmma_hrs_n32<0>(Z[p], fr[4 * p], fr[4 * p + 2], fr[4 * p + 1], fr[4 * p + 3], dsc(dfl, 32), 0);
    wgmma_hrs_n32<0>(Z[p], fi[4 * p], fi[4 * p + 2], fi[4 * p + 1], fi[4 * p + 3], dsc(dfl + 16, 32), 1);
  }
  wg_commit();
}
__device__ __forceinline__ void conv_win(const ConvC& K, const uint32_t (&X)[2][8], uint32_t (&W)[2][8]) {
#pragma unroll
  for (int b = 0; b < 4; b++)
#pragma unroll
    for (int c = 0; c < 2; c++) {
      const uint32_t xr = X[b >> 1][2 * c + (b & 1)], xi = X[b >> 1][4 + 2 * c + (b & 1)];
      const int a = b ? b - 1 : 0;
      W[b >> 1][2 * c + (b & 1)] = b ? hfnma(K.sg, X[a >> 1][4 + 2 * c + (a & 1)], xr) : hmul16(xr, 0x3C003C00u);
      W[b >> 1][4 + 2 * c + (b & 1)] = b ? hfma(K.sg, X[a >> 1][2 * c + (a & 1)], xi) : hmul16(xi, 0x3C003C00u);
    }
}
template <int p>
__device__ __forceinline__ void conv_pw(uint32_t (&X)[2][8], uint32_t (&H)[2][8], uint32_t (&V)[8], uint32_t dil) {
  uint32_t pr[2][2], pi[2][2];
#pragma unroll
  for (int jj = 0; jj < 2; jj++)
#pragma unroll
    for (int c = 0; c < 2; c++) {
      const int j = 2 * p + jj;
      uint32_t sr = 0, si = 0;
#pragma unroll
      for (int a = 0; a <= j; a++) {
        const int b = j - a;
        const uint32_t hr = H[a >> 1][2 * c + (a & 1)], hi = H[a >> 1][4 + 2 * c + (a & 1)];
        const uint32_t xr = X[b >> 1][2 * c + (b & 1)], xi = X[b >> 1][4 + 2 * c + (b & 1)];
        sr = a == 0 ? hmul16(hr, xr) : hfma(hr, xr, sr);
        si = a == 0 ? hmul16(hr, xi) : hfma(hr, xi, si);
        sr = hfnma(hi, xi, sr);
        si = hfma(hi, xr, si);
      }
      pr[jj][c] = sr; pi[jj][c] = si;
    }
  wg_fence();
  wgmma_hrs_n32<0>(V, pr[0][0], pr[1][0], pr[0][1], pr[1][1], dsc(dil, 32), 0);
  wgmma_hrs_n32<0>(V, pi[0][0], pi[1][0], pi[0][1], pi[1][1], dsc(dil + 16, 32), 1);
  wg_commit();
}
template <int p>
__device__ __forceinline__ void conv_it(const ConvC& K, uint32_t (&V)[8], uint32_t vst) {
#pragma unroll
  for (int jj = 0; jj < 2; jj++) {
    uint32_t wr[2], wi[2];
#pragma unroll
    for (int c = 0; c < 2; c++) {
      const uint32_t r = hfnma(K.wa[c], V[4 + 2 * c + jj], V[2 * c + jj]);
      wi[c] = hfnma(K.wb[c], r, V[4 + 2 * c + jj]);
      wr[c] = hfnma(K.wa[c], wi[c], r);
    }
    stsm4(vst + (2 * p + jj) * 2048, wr[0], wr[1], wi[0], wi[1]);
  }
}
__device__ __forceinline__ void conv_m4(uint32_t (&y)[8], uint32_t (&a)[4][4], uint32_t d4l) {
  wg_fence();
  wgmma_hrs_n32<0>(y, a[0][0], a[0][1], a[0][2], a[0][3], dsc(d4l, 64), 0);
#pragma unroll
  for (int s = 1; s < 4; s++) wgmma_hrs_n32<0>(y, a[s][0], a[s][1], a[s][2], a[s][3], dsc(d4l + s * 16, 64), 1);
  wg_commit();
}

struct Params {
  CUtensorMap tmX0, tmW, tmX, tmWo, tmWo1, tmK, tmV, tmQ, tmOA, tmOB;
  const __nv_bfloat16 *shift_k, *h, *D, *x, *w, *wo, *q;
  float *part, *kv;
  uint4* o;
  unsigned *ocnt, *epoch;
  const uint32_t *thr, *img;
};

__global__ void __cluster_dims__(2, 1, 1) __launch_bounds__(384, 1) fused_kernel(const __grid_constant__ Params P) {
  extern __shared__ __align__(1024) uint8_t smem[];
  const uint32_t sb = __shfl_sync(~0u, smem_u32(smem), 0);
  const uint32_t bars = sb + OFF_BAR;
  const int tid = threadIdx.x, lane = tid & 31;
  const int warp = __shfl_sync(~0u, tid >> 5, 0);
  const int rank = blockIdx.x & 1, cl = blockIdx.x >> 1;
  const unsigned c7 = cl + 6, g7 = (c7 * 37) >> 8;
  const int mb = cl < 4 ? 4 + cl : cl < 36 ? (cl - 4) >> 3 : g7 - 2;
  const int hq = cl < 4 ? 0 : cl < 36 ? (cl - 4) & 7 : 1 + c7 - 7 * g7;
  const int hp = 2 * hq + rank;
  const int rb = 2 * mb + (hq >> 2), cb = hq & 3;
#define BAR(i) (bars + 8 * (i))

  if (tid == 0) { STAMP(0, 0); GSTAMP(0, 30); }
  if (warp == 8) {
    if (elect_one()) {
      mbar_init(BAR(B_FULL1), 1);
      mbar_init(BAR(B_FIRST), 1);
      asm volatile("fence.mbarrier_init.release.cluster;" ::: "memory");
      mbar_expect(BAR(B_FIRST), STAGE_BYTES - 16384);
      tma2d(sb, &P.tmX0, 0, mb * 256, BAR(B_FIRST));
      tma2d(sb + 16384, &P.tmX0, 0, mb * 256 + 128, BAR(B_FIRST));
      tma3d(sb + 32768, &P.tmW, hp * 64, 0, 0, BAR(B_FIRST));
    }
    if (lane == 0) STAMP(3, 21);
  } else if (lane == 0) {
    const int wi = warp - (warp > 8);
#pragma unroll
    for (int r = 0; r < 6; r++)
      if (r < 5 || wi < B_COUNT - 56) mbar_init(BAR(1 + 11 * r + wi), ((uint32_t)(bar_counts(r) >> (4 * wi)) & 15) + 1);
    asm volatile("fence.mbarrier_init.release.cluster;" ::: "memory");
  }
  if (tid == 0) STAMP(2, 6);
  asm volatile("barrier.cluster.arrive.relaxed.aligned;\nbarrier.cluster.wait.aligned;" ::: "memory");
  if (warp == 8 && elect_one()) {
    mbar_expect(BAR(B_FULL1), 16384);
    tma2d_mc(sb + 8192 + rank * 16384, &P.tmX0, 0, mb * 256 + 64 + rank * 128, BAR(B_FULL1));
  }
  if (tid == 256) STAMP(2, 7);

  if (warp < 8) {
    asm volatile("setmaxnreg.inc.sync.aligned.u32 224;");
    const int wg = warp >> 2, w = warp & 3, g = lane >> 2, q = lane & 3, t = tid & 127;
    const bool elect = (t == 0);
    const uint32_t s16 = (sb & 0x3FFFF) >> 4;
    uint32_t pq[2][16], ux[16], uh[16], X[4][2][8], H[4][2][8];
    ConvC K;
    const uint32_t dfl = s16 + (OFF_F2F >> 4) + (8 << 16), dil = s16 + (OFF_F2I >> 4) + (8 << 16), d4l = s16 + (OFF_F4 >> 4) + (8 << 16);
    const uint32_t xl = s16 + (OFF_XT >> 4) + 4 * wg * (XT_STRIDE >> 4) + (8 << 16);
    const uint32_t hl = s16 + (OFF_H >> 4) + wg * 512 + (8 << 16);
    {
      float acc[2][96];
      if (SPLIT0) {
#pragma unroll
        for (int mt = 0; mt < 2; mt++) {
          mbar_wait(BAR(mt ? B_FULL1 : B_FIRST), 0);
          if (mt == 0 && elect) { STAMP(wg, 1); GSTAMP(wg, 26); }
          wg_fence();
#pragma unroll
          for (int ks = 0; ks < 4; ks++)
            wgmma_ss_n192<0, 1>(acc[mt], dsc(s16 + wg * 1024 + mt * 512 + (1 << 16) + ks * 2, SW128), dsc(s16 + 2048 + (512 << 16) + ks * 128, SW128), ks != 0);
        }
        wg_commit();
      }
      int st = SPLIT0 ? 1 : 0, ph = 0;
#pragma unroll 1
      for (int kb = SPLIT0 ? 1 : 0; kb < 14; kb++) {
        mbar_wait(BAR(B_FULL1 + st), ph);
        if (kb == 0 && elect) { STAMP(wg, 1); GSTAMP(wg, 26); }
        if (kb == 8 && elect) { STAMP(wg, 16); GSTAMP(wg, 25); }
        const uint32_t da = s16 + st * (STAGE_BYTES >> 4) + wg * 1024 + (1 << 16);
        const uint32_t db = s16 + st * (STAGE_BYTES >> 4) + 2048 + (512 << 16);
        wg_fence();
#pragma unroll
        for (int ks = 0; ks < 4; ks++) {
          wgmma_ss_n192<0, 1>(acc[0], dsc(da + ks * 2, SW128), dsc(db + ks * 128, SW128), (kb | ks) != 0);
          wgmma_ss_n192<0, 1>(acc[1], dsc(da + 512 + ks * 2, SW128), dsc(db + ks * 128, SW128), (kb | ks) != 0);
        }
        wg_commit();
        wg_wait<1>();
        if (kb > 0 && t < 2) mbar_arrive_cl(BAR(B_EMPTY1 + (st == 0 ? 2 : st - 1)), t);
        if (++st == 3) { st = 0; ph ^= 1; }
      }
#define TAIL_MMA(mt, stage) do { wg_fence(); _Pragma("unroll") for (int ks = 0; ks < 4; ks++) \
        wgmma_ss_n192<0, 1>(acc[mt], dsc(s16 + (stage) * (STAGE_BYTES >> 4) + wg * 1024 + (mt) * 512 + (1 << 16) + ks * 2, SW128), \
                            dsc(s16 + (stage) * (STAGE_BYTES >> 4) + 2048 + (512 << 16) + ks * 128, SW128), 1); wg_commit(); } while (0)
      mbar_wait(BAR(B_FULL1 + 2), 0);
      TAIL_MMA(0, 2);
      wg_wait<1>();
      if (elect) mbar_arrive(BAR(B_SFREE));
      mbar_wait(BAR(B_FULL1 + 0), 1);
      TAIL_MMA(0, 0);
      TAIL_MMA(1, 2);
      const uint32_t lrow = sb + wg * 16384 + (16 * w + 8 * ((lane >> 3) & 1) + (lane & 7)) * 128 + (((lane >> 4) ^ (lane & 7)) << 4);
#define E1K(mt, i) do { if (opaque_true()) { _Pragma("unroll") for (int j = (i); j < (i) + 2; j++) { \
          const float* a = &acc[mt][32 + 8 * j]; const float* b = a + 32; const uint32_t o = (lrow ^ (j * 32)) + (mt) * 8192; \
          stsm4(o + 2 * STAGE_BYTES, pk2(b[0], b[1]), pk2(b[2], b[3]), pk2(b[4], b[5]), pk2(b[6], b[7])); \
          stsm4(o, phi2(a[0], a[1]), phi2(a[2], a[3]), phi2(a[4], a[5]), phi2(a[6], a[7])); } } } while (0)
#define E1Q(mt) do { if (opaque_true()) { _Pragma("unroll") for (int i = 0; i < 16; i++) pq[mt][i] = phi2(acc[mt][2 * i], acc[mt][2 * i + 1]); } } while (0)
#define LOAD_K() do { const uint4* ct = (const uint4*)P.thr + t; \
        _Pragma("unroll") for (int s = 0; s < 2; s++) { const uint4 u = ld_na4(ct + s * 128); K.a1[s][0] = u.x; K.a1[s][1] = u.y; K.a1[s][2] = u.z; K.a1[s][3] = u.w; } \
        const uint4 u = ld_na4(ct + 2 * 128); K.wa[0] = u.x; K.wa[1] = u.y; K.wb[0] = u.z; K.wb[1] = u.w; \
        K.sg = (lane & 4) ? 0xBC00BC00u : 0x3C003C00u; } while (0)
#define PK_READY(mt) do { fence_async(); __syncwarp(); if (lane == 0) mbar_arrive(BAR(B_PKRDY + (mt))); } while (0)
      wg_wait<1>();
      keep(acc[0]);
      if (elect) STAMP(wg, 18);
      E1K(0, 0);
      TAIL_MMA(1, 0);
      E1K(0, 2);
      if (elect) STAMP(wg, 19);
      PK_READY(0);
      wg_wait<0>();
      keep(acc[1]);
      if (elect) mbar_arrive(BAR(B_G1DONE));
      asm volatile("setmaxnreg.dec.sync.aligned.u32 200;");
      if (elect) { STAMP(wg, 2); GSTAMP(wg, 27); }
      E1K(1, 0);
      if (elect) STAMP(wg, 20);
      E1K(1, 2);
      if (elect) STAMP(wg, 21);
      PK_READY(1);
      if (elect) STAMP(wg, 3);
      LOAD_K();
      if (elect) STAMP(wg, 4);
      E1Q(0);
      E1Q(1);
      if (elect) STAMP(wg, 17);
      mbar_wait(BAR(B_H), 0);
      conv_m1(K, ux, xl);
      conv_m1(K, uh, hl);
      wg_wait<1>(); keepu(ux);
      if (lane == 0) mbar_arrive_cl(BAR(B_XFREE + 4 * wg), rank ^ 1);
      conv_s2(K, ux, X[0], dfl);
      wg_wait<1>(); keepu(uh);
      conv_s2(K, uh, H[0], dfl);
    }
    if (elect) STAMP(wg, 5);
    {
      uint32_t vst = sb + wg * 8192 + w * 512 + lane * 16, vld = sb + wg * 8192 + w * 2048 + lane * 16;
      uint32_t ya = mapa(sb + OFF_XT + 4 * wg * XT_STRIDE + (2 * rank + (w & 1)) * 1024 + lane * 16, w >> 1);
      const uint32_t ybar = mapa(BAR(B_Y), w >> 1);
      asm volatile("" : "+r"(vst), "+r"(vld), "+r"(ya));
      uint32_t W[2][8], V0[8], V1[8], y[8], a[4][4];
      uint4 ov[4];
      uint4* const ot = P.o + ((2 * mb + wg) * 16 + hq) * 1024 + (16 * w + g) * 8 + ((4 * rank + q) ^ g);
#define YOUT(i) do { if ((w >> 1) == rank) { \
          asm volatile("st.shared.v4.b32 [%0], {%1,%2,%3,%4};" ::"r"(ya + (i) * XT_STRIDE), "r"(y[0]), "r"(y[2]), "r"(y[4]), "r"(y[6]) : "memory"); \
          asm volatile("st.shared.v4.b32 [%0], {%1,%2,%3,%4};" ::"r"(ya + (i) * XT_STRIDE + 512), "r"(y[1]), "r"(y[3]), "r"(y[5]), "r"(y[7]) : "memory"); \
        } else { \
          mbar_wait(BAR(B_XFREE + 4 * wg + (i)), 0); \
          st_async4(ya + (i) * XT_STRIDE, y[0], y[2], y[4], y[6], ybar); \
          st_async4(ya + (i) * XT_STRIDE + 512, y[1], y[3], y[5], y[7], ybar); } } while (0)
      auto ocalc = [&](const int hh) {
        if (hh == 0) {
          if (elect) STAMP(wg, 8);
          mbar_wait(BAR(B_KV), 0);
          if (elect) STAMP(wg, 9);
        }
        float oa[2][20];
        wg_fence();
#pragma unroll
        for (int m = 0; m < 4; m++) {
          const uint32_t* p = &pq[m & 1][8 * hh + 4 * (m >> 1)];
          wgmma_rs_n40<1>(oa[m & 1], p[0], p[1], p[2], p[3], dsc(s16 + (OFF_KVB >> 4) + hh * 160 + (m >> 1) * 16 + (8 << 16), 32), m >> 1);
        }
        wg_commit();
        wg_wait<0>();
#pragma unroll
        for (int mt = 0; mt < 2; mt++) {
          float (&o)[20] = oa[mt];
          keep(o);
          const uint32_t den = hadd(pk2(o[16], o[18]), 0x35863586u);
#pragma unroll
          for (int r = 0; r < 2; r++) {
            const float ri = rcp_fast(__uint_as_float(r ? (den & 0xFFFF0000u) : (den << 16)));
            uint4 u;
            u.x = pk2(o[2 * r] * ri, o[2 * r + 1] * ri);
            u.y = pk2(o[4 + 2 * r] * ri, o[5 + 2 * r] * ri);
            u.z = pk2(o[8 + 2 * r] * ri, o[9 + 2 * r] * ri);
            u.w = pk2(o[12 + 2 * r] * ri, o[13 + 2 * r] * ri);
            if (hh == 0) st_cg4(ot + (64 * mt + 8 * r) * 8, u); else ov[2 * mt + r] = u;
          }
        }
        if (hh == 0) {
          __syncwarp();
          if (lane == 0) mbar_arrive(BAR(B_ODONE));
          if (elect) STAMP(wg, 10);
        }
      };
      auto trickle = [&](const int qs) {
        const int m = qs - 2 * (OCH + O1D) - (TRICK - 1);
        if (m >= 0 && m < 4) {
          st_cg4(ot + 8 * 1024 + (64 * (m >> 1) + 8 * (m & 1)) * 8, ov[m]);
          if (m == 3) { __syncwarp(); if (lane == 0) mbar_arrive(BAR(B_ODONE1)); }
        }
      };
#pragma unroll
      for (int i = 0; i < 4; i++) {
        const bool nx = i < 3;
        const int n = nx ? i + 1 : i;
        const uint32_t vo = (i & 1) ? OFF_H + (i >> 1) * 16384 : OFF_VP;
        if (2 * i == OCH) ocalc(0);
        if (2 * i == OCH + O1D) ocalc(1);
        if (nx) {
          conv_m1(K, ux, xl + n * (XT_STRIDE >> 4));
          conv_m1(K, uh, hl + (n >> 1) * 1024 + (n & 1) * 256);
        }
        if (2 * i != OCH && 2 * i != OCH + O1D) { if (nx) { if (i > 0) wg_wait<3>(); else wg_wait<2>(); } else wg_wait<1>(); }
        keepu(X[i][0]); keepu(X[i][1]); keepu(H[i][0]); keepu(H[i][1]);
        conv_win(K, X[i], W);
        trickle(4 * i);
        conv_pw<0>(W, H[i], V0, dil);
        conv_pw<1>(W, H[i], V1, dil);
        trickle(4 * i + 1);
        wg_wait<2>();
        if (i > 0) { keepu(y); YOUT(i - 1); }
        if (2 * i + 1 == OCH) ocalc(0);
        if (2 * i + 1 == OCH + O1D) ocalc(1);
        if (nx) {
          keepu(ux); keepu(uh);
          if (lane == 0) mbar_arrive_cl(BAR(B_XFREE + 4 * wg + n), rank ^ 1);
          conv_s2(K, ux, X[n], dfl);
          wg_wait<1>();
        } else wg_wait<0>();
        keepu(V0); keepu(V1);
        trickle(4 * i + 2);
        if (i == 0) mbar_wait(BAR(B_H2), 0);
        conv_it<0>(K, V0, vst + vo);
        conv_it<1>(K, V1, vst + vo);
        bar_sync(1 + wg);
#pragma unroll
        for (int s = 0; s < 4; s++) ldsm4t(a[s], vld + vo + s * 512);
        if (nx) conv_s2(K, uh, H[n], dfl);
        conv_m4(y, a, d4l);
        trickle(4 * i + 3);
        if (i > 0 && lane < 2) mbar_arrive_cl(BAR(B_AFREE + i - 1), lane);
        if (elect && i < 3) STAMP(wg, i < 2 ? 6 + i : 9 + i);
      }
      wg_wait<0>(); keepu(y);
      YOUT(3);
      __syncwarp();
      if (lane == 0) mbar_arrive(BAR(B_Y));
      if (elect) STAMP(wg, 12);
    }
    {
      float acc[64];
#define G2_MMA(da, db, first) do { wg_fence(); _Pragma("unroll") for (int ks = 0; ks < 4; ks++) \
        wgmma_ss_n128<0, 1>(acc, dsc((da) + ks * 2, SW128), dsc((db) + ks * 128, SW128), ks || !(first)); wg_commit(); } while (0)
      const uint32_t a0 = s16 + wg * 512 + (1 << 16), b0 = s16 + (512 << 16);
      uint64_t ta = SLOT_A, tb = SLOT_B;
      uint32_t da = a0 + (SLOT_A & 15) * 1024, db = b0 + (SLOT_B & 15) * 1024, fb = BAR(B_FULL2);
      uint32_t cons = mapa(BAR(B_CONS2 - 1), t & 1);
      const bool rel = __shfl_sync(~0u, t, lane) < 2;
#pragma unroll 1
      for (int kb = 0; kb < HOLD2; kb++) {
        mbar_wait(fb, 0);
        if (kb == 0 && elect) { STAMP(wg, 13); GSTAMP(wg, 28); }
        G2_MMA(da, db, kb == 0);
        ta >>= 4; tb >>= 4;
        da = a0 + ((uint32_t)ta & 15) * 1024; db = b0 + ((uint32_t)tb & 15) * 1024; fb += 8;
        asm volatile("" : "+r"(da), "+r"(db));
        wg_wait<1>();
        if (kb > 0 && kb < 12 && rel) asm volatile("mbarrier.arrive.shared::cluster.b64 _, [%0];" ::"r"(cons) : "memory");
        cons += 8;
      }
#pragma unroll
      for (int kb = HOLD2; kb < 16; kb++) {
        if (wg == 1) mbar_wait(BAR(B_FULL2 + kb), 0);
        else if (kb == HOLD2) asm volatile("bar.sync 3, 256;" ::: "memory");
        G2_MMA(a0 + ((SLOT_A >> (4 * kb)) & 15) * 1024, b0 + ((SLOT_B >> (4 * kb)) & 15) * 1024, false);
      }
      if (wg == 1) asm volatile("bar.arrive 3, 256;" ::: "memory");
      const uint32_t stg = sb + wg * 8192 + w * 2048, so0 = ((SLOT_A >> 56) & 15) * 16384, so1 = ((SLOT_A >> 60) & 15) * 16384;
      const uint32_t lrow = stg + (8 * ((lane >> 3) & 1) + (lane & 7)) * 128 + (((lane >> 4) ^ (lane & 7)) << 4);
      const int col = 1024 + 256 * cb + 128 * rank, row = 128 * rb + 64 * wg + 16 * w;
      wg_wait<0>();
      keep(acc);
      if (elect) { STAMP(wg, 14); GSTAMP(wg, 29); }
#pragma unroll
      for (int cp = 0; cp < 8; cp++) {
        const float* a = &acc[8 * cp];
        stsm4((lrow ^ ((cp & 3) * 32)) + (cp >> 2 ? so1 : so0), pk2(a[0], a[1]), pk2(a[2], a[3]), pk2(a[4], a[5]), pk2(a[6], a[7]));
        if ((cp & 3) == 3) {
          fence_async();
          __syncwarp();
          if (elect_one()) tma2d_st(&P.tmOB, stg + (cp >> 2 ? so1 : so0), col + (cp >> 2) * 64, row);
        }
      }
      asm volatile("cp.async.bulk.commit_group;\ncp.async.bulk.wait_group.read 0;" ::: "memory");
      if (elect) {
        STAMP(wg, 15); GSTAMP(wg, 31); PDUMP(wg); if (wg == 0) PDUMP(2);
      }
    }
  } else {
    asm volatile("setmaxnreg.dec.sync.aligned.u32 56;");
    const int hw = warp - 9, g = lane >> 2, q = lane & 3;
#define sbar (bars + 8 * (B_STG - 18) + 16 * warp)
    if (warp == 8) {
      if (D1) __nanosleep(D1);
      int st = 1, pp = 1;
      const uint8_t* pfx = (const uint8_t*)P.x + (mb * 256 + hp * 16 + (lane & 15)) * 2048;
      const uint8_t* pfw = (const uint8_t*)P.w + (mb * 8 + (lane & 7)) * 6144 + (lane >> 3) * 2048 + hp * 128;
#pragma unroll 1
      for (int kb = 1; kb < 16; kb++) {
        if (kb >= 3) mbar_wait(BAR(B_EMPTY1 + st), pp);
        const uint32_t sa = sb + st * STAGE_BYTES;
        if (elect_one()) {
          mbar_expect(BAR(B_FULL1 + st), STAGE_BYTES);
          tma2d_mc(sa + rank * 16384, &P.tmX, kb * 64, mb * 256 + rank * 128, BAR(B_FULL1 + st));
          tma3d(sa + 32768, &P.tmW, hp * 64, kb * 64, 0, BAR(B_FULL1 + st));
        }
        if (kb == 1 && lane == 0) STAMP(2, 24);
        if (PFD && kb >= 2) {
#pragma unroll 1
          for (int j = kb == 2 ? 3 : kb + PFD; j <= kb + PFD && j < 16; j++) {
            if (lane < 16) asm volatile("prefetch.global.L2 [%0];" ::"l"(pfx + j * 128));
            if (lane < 24) asm volatile("prefetch.global.L2 [%0];" ::"l"(pfw + j * (64 * 6144)));
          }
          if (kb >= QPF && kb < QPF + 8) asm volatile("prefetch.global.L2 [%0];" ::"l"((const uint8_t*)P.q + (blockIdx.x * 256 + (kb - QPF) * 32 + lane) * 128));
          if (kb >= 4)
            asm volatile("prefetch.global.L2 [%0];" ::"l"(kb < 12 ? (const uint8_t*)P.h + ((2 * cl + rank) * 256 + (kb - 4) * 32 + lane) * 128
                                                                  : (const uint8_t*)P.wo + (blockIdx.x * 128 + (kb - 12) * 32 + lane) * 128));
        }
        if (++st == 3) { st = 0; pp ^= 1; }
      }
      if (lane == 0) STAMP(2, 1);
    } else {
      {
        const uint32_t clk0 = __shfl_sync(~0u, (uint32_t)clock(), 0), stg = sb + OFF_STG + hw * STG_STRIDE;
        const unsigned epoch = __shfl_sync(~0u, P.epoch[blockIdx.x], 0);
        const uint32_t tag = ~epoch & 1;
        uint32_t tap[2][4];
#pragma unroll
        for (int cg = 0; cg < 2; cg++) {
          const uint2 u = __ldg((const uint2*)(P.shift_k + (16 * cl + 8 * cg + g) * 4));
          tap[cg][0] = __byte_perm(u.x, 0, 0x1010); tap[cg][1] = __byte_perm(u.x, 0, 0x3232);
          tap[cg][2] = __byte_perm(u.y, 0, 0x1010); tap[cg][3] = __byte_perm(u.y, 0, 0x3232);
        }
        if (hw == 0 && lane < 8) *(float*)(smem + OFF_D + 4 * lane) = __bfloat162float(P.D[16 * cl + 8 * rank + lane]);
        if (hw == 1 && lane < 24) asm volatile("prefetch.global.L2 [%0];" ::"l"(P.thr + (lane + 24 * rank) * 32));
        if (hw == 0 && elect_one()) {
          *(volatile unsigned*)(smem + OFF_EPOCH) = epoch;
          mbar_expect(BAR(B_XRAW), 16384);
          mbar_expect(BAR(B_Y), 16384 + 64);
        }
        for (int i = hw * 32 + lane; i < 528; i += 96) st_tag4(P.part + (hp * 8 + mb) * 2176 + 4 * i, 0.f, 0.f, 0.f, 0.f, tag ^ 1);
        if (hw < 2 || lane < 2) st_tag4(P.kv + hp * 2176 + (4 * (hw < 2 ? 64 * mb + 32 * hw + lane : 512 + 2 * mb + lane)), 0.f, 0.f, 0.f, 0.f, tag ^ 1);
        if (lane == 0) STAMP(3, hw);
        const uint32_t xo = sb + OFF_XT + g * XT_STRIDE + rank * 2048 + q * 4;
        const int krow = 8 + (lane & 7) - (lane >> 3);
        const uint32_t ka = stg + krow * 32 + ((krow & 4) << 2), va = stg + 2304 + lane * 32 + ((lane & 4) << 2);
        int ph = 0, b = 0;
#pragma unroll 1
        for (int ci = hw - 3; ci < 16; ci += 3) {
          const uint32_t bo = b ? OFF_F2F - OFF_STG : 0, bn = b ? 0 : OFF_F2F - OFF_STG;
          if (ci + 3 < 16) {
            while (__any_sync(~0u, (uint32_t)clock() - clk0 < HSTART + (ci + 3) * PACE)) __nanosleep(64);
            if (elect_one()) {
              mbar_expect(sbar + 8 * (b ^ 1), 2304 + 2048);
              tma2d(stg + bn, &P.tmK, 16 * cl, 1024 * rank + 64 * (ci + 3) - 8, sbar + 8 * (b ^ 1));
              tma2d(stg + bn + 2304, &P.tmV, 16 * cl, 1024 * rank + 64 * (ci + 3), sbar + 8 * (b ^ 1));
            }
          }
          if (ci >= 0) {
            mbar_wait(sbar + 8 * b, (ph >> b) & 1);
            ph ^= 1 << b;
#pragma unroll 1
            for (int grp = 0; grp < 2; grp++) {
#pragma unroll
              for (int cg = 0; cg < 2; cg++) {
                const uint32_t dst = mapa(xo + (ci >> 3) * 1024 + ((ci & 7) * 4 + 2 * grp) * 16, cg), xbar = mapa(BAR(B_XRAW), cg);
                uint32_t vv[4], kk[4][4];
                ldsm4t(vv, (va ^ (cg * 16)) + bo + grp * 1024);
#pragma unroll
                for (int rg = 0; rg < 4; rg++) ldsm4t(kk[rg], (ka ^ (cg * 16)) + bo + grp * 1024 + rg * 256);
#pragma unroll
                for (int rg = 0; rg < 4; rg++)
                  vv[rg] = hmul(hadd(hadd(hadd(hmul(kk[rg][3], tap[cg][3]), hmul(kk[rg][2], tap[cg][2])), hmul(kk[rg][1], tap[cg][1])), hmul(kk[rg][0], tap[cg][0])), vv[rg]);
                if (cg == rank) {
#pragma unroll
                  for (int rg = 0; rg < 4; rg++) asm volatile("st.shared.b32 [%0], %1;" ::"r"(dst + (rg & 1) * 512 + (rg >> 1) * 16), "r"(vv[rg]) : "memory");
                } else {
#pragma unroll
                  for (int rg = 0; rg < 4; rg++) st_async(dst + (rg & 1) * 512 + (rg >> 1) * 16, vv[rg], xbar);
                }
              }
            }
          }
          b ^= 1;
        }
      }
      if (lane == 0) STAMP(3, 3 + hw);
      asm volatile("bar.sync 4, 96;" ::: "memory");
      if (hw == 0 && elect_one()) { mbar_expect(BAR(B_XT), 10240); bulk_ld(sb + OFF_F2F, P.img, 10240, BAR(B_XT)); }
      mbar_wait(BAR(B_XRAW), 0);
    }
    int e1 = 0;
#pragma unroll 1
    for (int n = hw < 0 ? 3 : 0; n < 4; n++) {
      const bool isH = n >= 3;
      const int c = isH ? (warp & 1) + 2 * (warp & 2) : hw + 3 * n;
      if (c < 8) {
        int ln;
        asm volatile("mov.u32 %0, %%laneid;" : "=r"(ln));
        uint8_t* dst = smem + (isH ? OFF_H + (c & 2) * 8192 + (c >> 2) * 8192 + (c & 1) * 4096 : OFF_XT + c * XT_STRIDE) + ((ln >> 4) * 512 + (ln & 15) * 16);
        const uint8_t* src0 = isH ? (const uint8_t*)P.h + (16 * cl + 8 * rank + c) * 4096 + ((ln & 15) * 32 + (ln & 16)) : dst;
        const uint8_t* src1 = src0 + (isH ? 512 : 256);
        uint32_t v[32];
#pragma unroll
        for (int i = 0; i < 8; i++) {
          const uint4 u = *(const uint4*)(((i & 1) ? src1 : src0) + (i >> 1) * 1024);
          v[4 * i] = u.x; v[4 * i + 1] = u.y; v[4 * i + 2] = u.z; v[4 * i + 3] = u.w;
        }
        if (isH) mbar_wait(BAR(B_XT), 0);
        const float f0 = __uint_as_float(v[0] << 16) + ((isH && ln == 0) ? *(const float*)(smem + OFF_D + 4 * c) : 0.f);
        const int e = norm_exp(v, f0);
        norm_cvt(v, f0, e);
        if (isH) mbar_wait(BAR(B_SFREE), 0);
        else if (ln == 0) smem[OFF_EX + c] = e;
        e1 = e;
#pragma unroll
        for (int i = 0; i < 8; i++)
          *(uint4*)(dst + (i >> 1) * 1024 + (i & 1) * 256) = make_uint4(v[4 * i], v[4 * i + 1], v[4 * i + 2], v[4 * i + 3]);
        if (n < 2 && elect_one()) {
          if (n == 0) mbar_expect(sbar, 4096);
          tma3d(sb + OFF_STG + 2048 * c, &P.tmQ, 16 * cl, 64 * rank, 2 * c, sbar);
        }
      }
      if (n >= 2) {
        fence_async();
        __syncwarp();
        if (lane == 0) { mbar_arrive(BAR(isH ? B_H : B_XT)); STAMP(3, (isH ? 17 : 13) + hw); }
      }
    }
#define SLOT(tab, kb) (sb + ((uint32_t)((tab) >> (4 * (kb))) & 15) * 16384)
#define LOAD_B(kb) tma4d(SLOT(SLOT_B, kb), &P.tmWo, 0, ((kb) >> 3) * 32, 2 * ((kb) & 7), 4 * cb + 2 * rank, BAR(B_FULL2 + (kb)))
#define LOAD_A(kb) bulk_ld_mc(SLOT(SLOT_A, kb) + rank * 8192, P.o + (rb * 16 + (kb)) * 1024 + rank * 512, 8192, BAR(B_FULL2 + (kb)))
    asm volatile("setmaxnreg.inc.sync.aligned.u32 104;");
    {
    int tid;
    asm volatile("mov.u32 %0, %%tid.x;" : "=r"(tid));
    const int lane = tid & 31, g = lane >> 2, q = lane & 3;
    const unsigned epoch = *(volatile unsigned*)(smem + OFF_EPOCH);
    const uint32_t tag = ~epoch & 1;
    const int pi = hw < 2 ? 64 * mb - 288 + tid : 512 + 2 * mb + (lane & 1);
    const float* psrc = P.part + hp * 8 * 2176 + 4 * pi;
    uint4 f[8];
    {
      const uint32_t s16 = (sb & 0x3FFFF) >> 4;
      const int t = tid & 127, c = 2 + (warp & 1) + 2 * (warp & 2);
      const uint4* hp4 = (const uint4*)(P.h + (16 * cl + 8 * rank + c) * 2048) + ((lane & 15) * 2 + (lane >> 4));
      uint32_t v[32];
#pragma unroll
      for (int i = 0; i < 8; i++) { const uint4 u = ld_na4(hp4 + i * 32); v[4 * i] = u.x; v[4 * i + 1] = u.y; v[4 * i + 2] = u.z; v[4 * i + 3] = u.w; }
      float kva[36];
#pragma unroll
      for (int mt = 0; mt < 2; mt++) {
        mbar_wait(BAR(B_PKRDY + mt), 0);
        wg_fence();
#pragma unroll
        for (int ks = 0; ks < 8; ks++) {
          const uint32_t o = (ks >> 2) * 1024 + mt * 512 + (ks & 3) * 128, vb = (2 * STAGE_BYTES >> 4) + o;
          wgmma_ss_n72<1, 1>(kva, dsc(s16 + o + (1 << 16), SW128), dsc(s16 + vb + (((OFF_ONES >> 4) - vb) << 16), SW128), (mt | ks) != 0);
        }
        wg_commit();
        if (mt == 0 && hw < 0) {
          mbar_wait(BAR(B_G1DONE), 0);
          if (elect_one()) {
#pragma unroll
            for (int kb = 0; kb < BEARLY; kb++) { mbar_expect(BAR(B_FULL2 + kb), 16384); LOAD_B(kb); }
          }
        }
      }
      float* pdst = P.part + (hp * 8 + mb) * 2176 + t * 4;
      float* zdst = P.part + (hp * 8 + mb) * 2176 + 2048 + (t >> 1);
      asm volatile("" : "+l"(pdst), "+l"(zdst));
      wg_wait<0>();
      keep(kva);
      if (hw < 1) {
#pragma unroll
        for (int c = 0; c < 4; c++) st_tag4(pdst + c * 512, kva[4 * c], kva[4 * c + 1], kva[4 * c + 2], kva[4 * c + 3], tag);
      } else {
#pragma unroll
        for (int c = 4; c < 8; c++) st_tag4(pdst + (c - 4) * 512, kva[4 * c], kva[4 * c + 1], kva[4 * c + 2], kva[4 * c + 3], tag);
      }
      const float z2 = __shfl_down_sync(~0u, kva[32], 4), z3 = __shfl_down_sync(~0u, kva[34], 4);
      if (!(lane & 7)) st_tag4(zdst, kva[32], kva[34], z2, z3, tag);
      if (lane == 0) mbar_arrive(BAR(B_PKFREE));
      const uint32_t cst = clock();
      if (hw == 0 && lane == 0) STAMP(3, 24);
      const float f0 = __uint_as_float(v[0] << 16) + (lane == 0 ? *(const float*)(smem + OFF_D + 4 * c) : 0.f);
      const int e = norm_exp(v, f0);
      norm_cvt(v, f0, e);
      if (hw >= 0) {
        while (__any_sync(~0u, (uint32_t)clock() - cst < PD1)) __nanosleep(20);
        if (hw == 0 && lane == 0) STAMP(3, 20);
#pragma unroll
        for (int p = 0; p < 8; p++) f[p] = ld_rlx4(psrc + p * 2176);
      }
      uint8_t* dst = smem + OFF_H + 16384 + (warp & 3) * 4096 + (lane >> 4) * 512 + (lane & 15) * 16;
#pragma unroll
      for (int i = 0; i < 8; i++)
        *(uint4*)(dst + (i >> 1) * 1024 + (i & 1) * 256) = make_uint4(v[4 * i], v[4 * i + 1], v[4 * i + 2], v[4 * i + 3]);
      if (lane < 4) {
        const int cc = c - (lane & 2);
        st_async(mapa(sb + OFF_SCALE + (8 * rank + cc) * 4, lane & 1), min(max(((lane & 2) ? e1 : e) + smem[OFF_EX + cc] - 124, 1), 254) << 23, mapa(BAR(B_Y), lane & 1));
      }
    }
#define H2_READY() do { fence_async(); __syncwarp(); if (lane == 0) mbar_arrive(BAR(B_H2)); } while (0)
    if (warp == 8) {
      H2_READY();
      mbar_wait(BAR(B_PKFREE), 0);
      {
        const uint32_t c0 = clock();
#pragma unroll 1
        for (int i = 0; i < 2 * NPRE - 2 * BEARLY; i++) {
          const int kb = (i >> 1) + BEARLY;
          while (__any_sync(~0u, (uint32_t)clock() - c0 < i * BPACE)) __nanosleep(32);
          if (elect_one()) {
            if (!(i & 1)) mbar_expect(BAR(B_FULL2 + kb), 16384);
            tma4d(SLOT(SLOT_B, kb) + (i & 1) * 8192, &P.tmWo1, 0, 0, 2 * kb, 4 * cb + 2 * rank + (i & 1), BAR(B_FULL2 + kb));
            if (i == 0) mbar_expect(BAR(B_Q), 8192);
            if (i < 4) tma3d(sb + OFF_SPARE + 2048 * i, &P.tmQ, 16 * cl, 64 * rank + 32 * (i >> 1), 2 * ((i + 6) & 7), BAR(B_Q));
          }
        }
      }
      if (lane == 0) STAMP(2, 2);
      mbar_wait(BAR(B_AFREE), 0);
      if (elect_one()) mbar_expect(BAR(B_FULL2), 16384);
      {
        const uint32_t dst = SLOT(SLOT_A, 0) + rank * 8192;
        const uint4* src = P.o + rb * 16 * 1024 + rank * 512;
        poll_ge(&P.ocnt[rb * 32], 16 * (epoch + 1));
        asm volatile("fence.proxy.async.global;" ::: "memory");
        if (lane == 0) STAMP(2, 3);
        if (elect_one()) bulk_ld_mc(dst, src, 8192, BAR(B_FULL2));
        if (lane == 0) STAMP(3, 23);
      }
#pragma unroll 1
      for (int kb = 1; kb < NPRE; kb++) {
        mbar_wait(BAR(kb < 4 ? B_AFREE + kb - 1 : B_CONS2), 0);
        if (elect_one()) { mbar_expect(BAR(B_FULL2 + kb), 16384); LOAD_A(kb); }
      }
#pragma unroll 1
      for (int kb = NPRE; kb < 16; kb++) {
        mbar_wait(BAR(B_CONS2 + kb - 5), 0);
        if (kb == 8) mbar_wait(BAR(B_O1RDY), 0);
        if (elect_one()) { mbar_expect(BAR(B_FULL2 + kb), 32768); LOAD_A(kb); LOAD_B(kb); }
      }
      if (lane == 0) { P.epoch[blockIdx.x] = epoch + 1; STAMP(2, 5); }
    } else {
      {
#pragma unroll 1
        for (int n = 0; __any_sync(~0u, stale8(f, tag) & 1); n++) {
#pragma unroll
          for (int p = 0; p < 8; p++) ld_stale4(f[p], psrc + p * 2176, tag);
          if (n > SPIN_LIMIT) __trap();
        }
        float s0 = 0.f, s1 = 0.f, s2 = 0.f, s3 = 0.f;
#pragma unroll
        for (int p = 0; p < 8; p++) { s0 += __uint_as_float(f[p].x); s1 += __uint_as_float(f[p].y); s2 += __uint_as_float(f[p].z); s3 += __uint_as_float(f[p].w); }
        if (hw < 2 || lane < 2) st_tag4(P.kv + hp * 2176 + (4 * pi), s0, s1, s2, s3, tag);
      }
      const uint32_t cs2 = clock();
      if (lane == 0 && hw == 0) STAMP(3, 8);
      H2_READY();
      if (hw == 2) {
        unsigned* cnt = P.ocnt + (2 * mb + lane) * 32;
#pragma unroll 1
        for (int hh = 0; hh < 2; hh++) {
          mbar_wait(BAR(hh ? B_ODONE1 : B_ODONE), 0);
          if (lane < 2) asm volatile("red.release.gpu.global.add.u32 [%0], 1;" ::"l"(cnt) : "memory");
          cnt += 512;
          if (lane == 0) STAMP(3, hh ? 6 : 7);
        }
        poll_ge(&P.ocnt[512 + rb * 32], 16 * (epoch + 1));
        asm volatile("fence.proxy.async.global;" ::: "memory");
        if (lane == 0) { mbar_arrive(BAR(B_O1RDY)); STAMP(2, 4); }
        __syncwarp();
      } else {
        const int t = tid - 288;
        const float* src = P.kv + hp * 2176 + (4 * t);
        const float* zsrc = P.kv + hp * 2176 + (2048 + (t & 48) + 2 * (lane & 6));
        while (__any_sync(~0u, (uint32_t)clock() - cs2 < PD2)) __nanosleep(20);
        uint4 zp = ld_rlx4(zsrc);
#pragma unroll
        for (int p = 0; p < 8; p++) f[p] = ld_rlx4(src + 4 * ((p & 3) * 128 + (p >> 2) * 64));
        if (!opaque_true()) __trap();
#pragma unroll 1
        for (int n = 0; __any_sync(~0u, (stale8(f, tag) | (zp.x ^ tag)) & 1); n++) {
          ld_stale4(zp, zsrc, tag);
#pragma unroll
          for (int p = 0; p < 8; p++) ld_stale4(f[p], src + 4 * ((p & 3) * 128 + (p >> 2) * 64), tag);
          if (n > SPIN_LIMIT) __trap();
        }
#define PK2U(a, b) pk2(__uint_as_float(a), __uint_as_float(b))
        const uint32_t zf = (lane & 1) ? ((lane & 8) ? zp.w : zp.z) : ((lane & 8) ? zp.y : zp.x);
        const uint32_t zz = PK2U(zf, zf);
        *(uint4*)(smem + OFF_KVB + hw * 2560 + 2048 + lane * 16) = make_uint4(zz, zz, zz, zz);
#pragma unroll
        for (int hh = 0; hh < 2; hh++) {
          const uint4* ff = &f[4 * hh];
          uint8_t* dst = smem + OFF_KVB + hh * 2560 + q * 512 + (16 * hw + g) * 16;
          *(uint4*)dst = make_uint4(PK2U(ff[0].x, ff[0].y), PK2U(ff[1].x, ff[1].y), PK2U(ff[2].x, ff[2].y), PK2U(ff[3].x, ff[3].y));
          *(uint4*)(dst + 128) = make_uint4(PK2U(ff[0].z, ff[0].w), PK2U(ff[1].z, ff[1].w), PK2U(ff[2].z, ff[2].w), PK2U(ff[3].z, ff[3].w));
        }
        fence_async();
        __syncwarp();
        if (lane == 0) { mbar_arrive(BAR(B_KV)); if (hw == 0) STAMP(3, 9); }
      }
#define QBUF(ci) (sb + 2048 * (ci) + ((ci) < 6 ? OFF_STG : (ci) < 10 ? OFF_SPARE - 6 * 2048 : OFF_F2F - 10 * 2048))
      mbar_wait(BAR(B_Y), 0);
      if (elect_one()) {
        mbar_expect(sbar + 8, 4096);
#pragma unroll 1
        for (int ci = hw ? hw + 9 : 12; ci < 16; ci += 3) tma3d(QBUF(ci), &P.tmQ, 16 * cl, 64 * rank + 32, 2 * (ci & 7), sbar + 8);
      }
      mbar_wait(BAR(B_Q), 0);
      mbar_wait(sbar, hw == 0);
      {
        const float2 sc0 = *(const float2*)(smem + OFF_SCALE + 8 * q), sc1 = *(const float2*)(smem + OFF_SCALE + 32 + 8 * q);
        const uint32_t yl = sb + OFF_XT + (lane & 7) * XT_STRIDE + (lane >> 3) * 16;
#pragma unroll 1
        for (int ci = hw; ci < 16; ci += 3) {
          const uint32_t qb = QBUF(ci);
          if (ci >= 10) mbar_wait(sbar + 8, 1);
#pragma unroll 1
          for (int nl = 0; nl < 2; nl++) {
            uint32_t yy[2][4], qq[2][4];
            const uint32_t qa = qb + lane * 32 + ((lane & 4) << 2) + nl * 1024;
#pragma unroll
            for (int cg = 0; cg < 2; cg++) { ldsm4t(yy[cg], yl + cg * 2048 + (2 * ci + nl) * 64); ldsm4(qq[cg], qa ^ (cg * 16)); }
#pragma unroll
            for (int cg = 0; cg < 2; cg++) {
              const float2 sc = cg ? sc1 : sc0;
#pragma unroll
              for (int m = 0; m < 4; m++) {
                const float2 f = __half22float2(*(const __half2*)&yy[cg][m]);
                qq[cg][m] = hmul(qq[cg][m], pk2(f.x * sc.x, f.y * sc.y));
              }
              stsm4(qa ^ (cg * 16), qq[cg][0], qq[cg][1], qq[cg][2], qq[cg][3]);
            }
          }
          fence_async();
          __syncwarp();
          if (elect_one()) tma3d_st(&P.tmOA, qb, 16 * cl, 64 * rank + 32 * (ci >> 3), 2 * (ci & 7));
        }
        asm volatile("cp.async.bulk.commit_group;\ncp.async.bulk.wait_group.read 0;" ::: "memory");
      }
      if (lane == 0) STAMP(3, 10 + hw);
    }
    }
  }
}

typedef CUresult (*EncodeFn)(CUtensorMap*, CUtensorMapDataType, cuuint32_t, void*, const cuuint64_t*, const cuuint64_t*,
                             const cuuint32_t*, const cuuint32_t*, CUtensorMapInterleave, CUtensorMapSwizzle,
                             CUtensorMapL2promotion, CUtensorMapFloatOOBfill);

static void enc(EncodeFn fn, CUtensorMap* m, const void* p, int rank, const cuuint64_t* dims, const cuuint64_t* strides,
                const cuuint32_t* box, CUtensorMapSwizzle swz, CUtensorMapL2promotion promo) {
  cuuint32_t es[4] = {1, 1, 1, 1};
  fn(m, CU_TENSOR_MAP_DATA_TYPE_BFLOAT16, rank, (void*)p, dims, strides, box, es, CU_TENSOR_MAP_INTERLEAVE_NONE, swz, promo,
     CU_TENSOR_MAP_FLOAT_OOB_FILL_NONE);
}

extern "C" void kernel_launch(void* const* d_in, const int* in_sizes, int n_in, void* d_out, int out_size) {
  void* fp = nullptr;
  cudaDriverEntryPointQueryResult qr;
  cudaGetDriverEntryPoint("cuTensorMapEncodeTiled", &fp, cudaEnableDefault, &qr);
  EncodeFn fn = (EncodeFn)fp;
  Params P;
  P.shift_k = (const __nv_bfloat16*)d_in[3]; P.h = (const __nv_bfloat16*)d_in[4]; P.D = (const __nv_bfloat16*)d_in[5];
  P.q = (const __nv_bfloat16*)d_in[0];
  cudaGetSymbolAddress((void**)&P.part, g_part); cudaGetSymbolAddress((void**)&P.kv, g_kv); cudaGetSymbolAddress((void**)&P.o, g_o);
  cudaGetSymbolAddress((void**)&P.ocnt, g_ocnt); cudaGetSymbolAddress((void**)&P.epoch, g_epoch);
  cudaGetSymbolAddress((void**)&P.thr, c_thr); cudaGetSymbolAddress((void**)&P.img, c_img);
  P.x = (const __nv_bfloat16*)d_in[6]; P.w = (const __nv_bfloat16*)d_in[7]; P.wo = (const __nv_bfloat16*)d_in[8];
  const CUtensorMapSwizzle S128 = CU_TENSOR_MAP_SWIZZLE_128B, S32 = CU_TENSOR_MAP_SWIZZLE_32B;
  const CUtensorMapL2promotion P0 = CU_TENSOR_MAP_L2_PROMOTION_NONE, P128 = CU_TENSOR_MAP_L2_PROMOTION_L2_128B;
  { cuuint64_t d[2] = {1024, 2048}, s[1] = {2048}; cuuint32_t b[2] = {64, 128}; enc(fn, &P.tmX, d_in[6], 2, d, s, b, S128, P128); }
  { cuuint64_t d[2] = {1024, 2048}, s[1] = {2048}; cuuint32_t b[2] = {64, 64}; enc(fn, &P.tmX0, d_in[6], 2, d, s, b, S128, P128); }
  { cuuint64_t d[3] = {1024, 1024, 3}, s[2] = {6144, 2048}; cuuint32_t b[3] = {64, 64, 3}; enc(fn, &P.tmW, d_in[7], 3, d, s, b, S128, P128); }
  { cuuint64_t d[4] = {64, 64, 16, 16}, s[3] = {2048, 131072, 128}; cuuint32_t b[4] = {64, 32, 2, 2}; enc(fn, &P.tmWo, d_in[8], 4, d, s, b, S128, P128); }
  { cuuint64_t d[4] = {64, 64, 16, 16}, s[3] = {2048, 131072, 128}; cuuint32_t b[4] = {64, 32, 2, 1}; enc(fn, &P.tmWo1, d_in[8], 4, d, s, b, S128, P128); }
  { cuuint64_t d[2] = {1024, 2048}, s[1] = {2048}; cuuint32_t b[2] = {16, 72}; enc(fn, &P.tmK, d_in[1], 2, d, s, b, S32, P128); }
  { cuuint64_t d[2] = {1024, 2048}, s[1] = {2048}; cuuint32_t b[2] = {16, 64}; enc(fn, &P.tmV, d_in[2], 2, d, s, b, S32, P128); }
  { cuuint64_t d[3] = {1024, 128, 16}, s[2] = {32768, 2048}; cuuint32_t b[3] = {16, 32, 2}; enc(fn, &P.tmQ, d_in[0], 3, d, s, b, S32, P128); }
  { cuuint64_t d[3] = {1024, 128, 16}, s[2] = {65536, 4096}; cuuint32_t b[3] = {16, 32, 2}; enc(fn, &P.tmOA, d_out, 3, d, s, b, S32, P0); }
  { cuuint64_t d[2] = {2048, 2048}, s[1] = {4096}; cuuint32_t b[2] = {64, 16}; enc(fn, &P.tmOB, d_out, 2, d, s, b, S128, P0); }
  cudaFuncSetAttribute(fused_kernel, cudaFuncAttributeMaxDynamicSharedMemorySize, SMEM_TOTAL);
  fused_kernel<<<128, 384, SMEM_TOTAL>>>(P);
}
```

```cpp
#include <cuda_runtime.h>
#include <cuda_bf16.h>
#include <cuda_fp16.h>
#include <cuda.h>
#include <stdint.h>

template<int TA, int TB, int SA=1> __device__ __forceinline__ void wgmma_ss_n192(float (&d)[96], uint64_t da, uint64_t db, int scale_d) {
  asm volatile("{\n.reg .pred p;\nsetp.ne.b32 p, %98, 0;\n"
    "wgmma.mma_async.sync.aligned.m64n192k16.f32.bf16.bf16 {%0, %1, %2, %3, %4, %5, %6, %7, %8, %9, %10, %11, %12, %13, %14, %15, %16, %17, %18, %19, %20, %21, %22, %23, %24, %25, %26, %27, %28, %29, %30, %31, %32, %33, %34, %35, %36, %37, %38, %39, %40, %41, %42, %43, %44, %45, %46, %47, %48, %49, %50, %51, %52, %53, %54, %55, %56, %57, %58, %59, %60, %61, %62, %63, %64, %65, %66, %67, %68, %69, %70, %71, %72, %73, %74, %75, %76, %77, %78, %79, %80, %81, %82, %83, %84, %85, %86, %87, %88, %89, %90, %91, %92, %93, %94, %95}, %96, %97, p, %101, 1, %99, %100;\n}\n"
    : "+f"(d[0]), "+f"(d[1]), "+f"(d[2]), "+f"(d[3]), "+f"(d[4]), "+f"(d[5]), "+f"(d[6]), "+f"(d[7]), "+f"(d[8]), "+f"(d[9]), "+f"(d[10]), "+f"(d[11]), "+f"(d[12]), "+f"(d[13]), "+f"(d[14]), "+f"(d[15]), "+f"(d[16]), "+f"(d[17]), "+f"(d[18]), "+f"(d[19]), "+f"(d[20]), "+f"(d[21]), "+f"(d[22]), "+f"(d[23]), "+f"(d[24]), "+f"(d[25]), "+f"(d[26]), "+f"(d[27]), "+f"(d[28]), "+f"(d[29]), "+f"(d[30]), "+f"(d[31]), "+f"(d[32]), "+f"(d[33]), "+f"(d[34]), "+f"(d[35]), "+f"(d[36]), "+f"(d[37]), "+f"(d[38]), "+f"(d[39]), "+f"(d[40]), "+f"(d[41]), "+f"(d[42]), "+f"(d[43]), "+f"(d[44]), "+f"(d[45]), "+f"(d[46]), "+f"(d[47]), "+f"(d[48]), "+f"(d[49]), "+f"(d[50]), "+f"(d[51]), "+f"(d[52]), "+f"(d[53]), "+f"(d[54]), "+f"(d[55]), "+f"(d[56]), "+f"(d[57]), "+f"(d[58]), "+f"(d[59]), "+f"(d[60]), "+f"(d[61]), "+f"(d[62]), "+f"(d[63]), "+f"(d[64]), "+f"(d[65]), "+f"(d[66]), "+f"(d[67]), "+f"(d[68]), "+f"(d[69]), "+f"(d[70]), "+f"(d[71]), "+f"(d[72]), "+f"(d[73]), "+f"(d[74]), "+f"(d[75]), "+f"(d[76]), "+f"(d[77]), "+f"(d[78]), "+f"(d[79]), "+f"(d[80]), "+f"(d[81]), "+f"(d[82]), "+f"(d[83]), "+f"(d[84]), "+f"(d[85]), "+f"(d[86]), "+f"(d[87]), "+f"(d[88]), "+f"(d[89]), "+f"(d[90]), "+f"(d[91]), "+f"(d[92]), "+f"(d[93]), "+f"(d[94]), "+f"(d[95])
    : "l"(da), "l"(db), "r"(scale_d), "n"(TA), "n"(TB), "n"(SA));
}
template<int TA, int TB, int SA=1> __device__ __forceinline__ void wgmma_ss_n128(float (&d)[64], uint64_t da, uint64_t db, int scale_d) {
  asm volatile("{\n.reg .pred p;\nsetp.ne.b32 p, %66, 0;\n"
    "wgmma.mma_async.sync.aligned.m64n128k16.f32.bf16.bf16 {%0, %1, %2, %3, %4, %5, %6, %7, %8, %9, %10, %11, %12, %13, %14, %15, %16, %17, %18, %19, %20, %21, %22, %23, %24, %25, %26, %27, %28, %29, %30, %31, %32, %33, %34, %35, %36, %37, %38, %39, %40, %41, %42, %43, %44, %45, %46, %47, %48, %49, %50, %51, %52, %53, %54, %55, %56, %57, %58, %59, %60, %61, %62, %63}, %64, %65, p, %69, 1, %67, %68;\n}\n"
    : "+f"(d[0]), "+f"(d[1]), "+f"(d[2]), "+f"(d[3]), "+f"(d[4]), "+f"(d[5]), "+f"(d[6]), "+f"(d[7]), "+f"(d[8]), "+f"(d[9]), "+f"(d[10]), "+f"(d[11]), "+f"(d[12]), "+f"(d[13]), "+f"(d[14]), "+f"(d[15]), "+f"(d[16]), "+f"(d[17]), "+f"(d[18]), "+f"(d[19]), "+f"(d[20]), "+f"(d[21]), "+f"(d[22]), "+f"(d[23]), "+f"(d[24]), "+f"(d[25]), "+f"(d[26]), "+f"(d[27]), "+f"(d[28]), "+f"(d[29]), "+f"(d[30]), "+f"(d[31]), "+f"(d[32]), "+f"(d[33]), "+f"(d[34]), "+f"(d[35]), "+f"(d[36]), "+f"(d[37]), "+f"(d[38]), "+f"(d[39]), "+f"(d[40]), "+f"(d[41]), "+f"(d[42]), "+f"(d[43]), "+f"(d[44]), "+f"(d[45]), "+f"(d[46]), "+f"(d[47]), "+f"(d[48]), "+f"(d[49]), "+f"(d[50]), "+f"(d[51]), "+f"(d[52]), "+f"(d[53]), "+f"(d[54]), "+f"(d[55]), "+f"(d[56]), "+f"(d[57]), "+f"(d[58]), "+f"(d[59]), "+f"(d[60]), "+f"(d[61]), "+f"(d[62]), "+f"(d[63])
    : "l"(da), "l"(db), "r"(scale_d), "n"(TA), "n"(TB), "n"(SA));
}
template<int TA, int TB, int SA=1> __device__ __forceinline__ void wgmma_ss_n72(float (&d)[36], uint64_t da, uint64_t db, int scale_d) {
  asm volatile("{\n.reg .pred p;\nsetp.ne.b32 p, %38, 0;\n"
    "wgmma.mma_async.sync.aligned.m64n72k16.f32.bf16.bf16 {%0, %1, %2, %3, %4, %5, %6, %7, %8, %9, %10, %11, %12, %13, %14, %15, %16, %17, %18, %19, %20, %21, %22, %23, %24, %25, %26, %27, %28, %29, %30, %31, %32, %33, %34, %35}, %36, %37, p, %41, 1, %39, %40;\n}\n"
    : "+f"(d[0]), "+f"(d[1]), "+f"(d[2]), "+f"(d[3]), "+f"(d[4]), "+f"(d[5]), "+f"(d[6]), "+f"(d[7]), "+f"(d[8]), "+f"(d[9]), "+f"(d[10]), "+f"(d[11]), "+f"(d[12]), "+f"(d[13]), "+f"(d[14]), "+f"(d[15]), "+f"(d[16]), "+f"(d[17]), "+f"(d[18]), "+f"(d[19]), "+f"(d[20]), "+f"(d[21]), "+f"(d[22]), "+f"(d[23]), "+f"(d[24]), "+f"(d[25]), "+f"(d[26]), "+f"(d[27]), "+f"(d[28]), "+f"(d[29]), "+f"(d[30]), "+f"(d[31]), "+f"(d[32]), "+f"(d[33]), "+f"(d[34]), "+f"(d[35])
    : "l"(da), "l"(db), "r"(scale_d), "n"(TA), "n"(TB), "n"(SA));
}
template<int TB, int SA=1> __device__ __forceinline__ void wgmma_rs_n40(float (&d)[20], uint32_t a0, uint32_t a1, uint32_t a2, uint32_t a3, uint64_t db, int scale_d) {
  asm volatile("{\n.reg .pred p;\nsetp.ne.b32 p, %25, 0;\n"
    "wgmma.mma_async.sync.aligned.m64n40k16.f32.bf16.bf16 {%0, %1, %2, %3, %4, %5, %6, %7, %8, %9, %10, %11, %12, %13, %14, %15, %16, %17, %18, %19}, {%20, %21, %22, %23}, %24, p, %27, 1, %26;\n}\n"
    : "+f"(d[0]), "+f"(d[1]), "+f"(d[2]), "+f"(d[3]), "+f"(d[4]), "+f"(d[5]), "+f"(d[6]), "+f"(d[7]), "+f"(d[8]), "+f"(d[9]), "+f"(d[10]), "+f"(d[11]), "+f"(d[12]), "+f"(d[13]), "+f"(d[14]), "+f"(d[15]), "+f"(d[16]), "+f"(d[17]), "+f"(d[18]), "+f"(d[19])
    : "r"(a0), "r"(a1), "r"(a2), "r"(a3), "l"(db), "r"(scale_d), "n"(TB), "n"(SA));
}
template<int TB> __device__ __forceinline__ void wgmma_hrs_n64(uint32_t (&d)[16], uint32_t a0, uint32_t a1, uint32_t a2, uint32_t a3, uint64_t db, int scale_d) {
  asm volatile("{\n.reg .pred p;\nsetp.ne.b32 p, %21, 0;\n"
    "wgmma.mma_async.sync.aligned.m64n64k16.f16.f16.f16 {%0, %1, %2, %3, %4, %5, %6, %7, %8, %9, %10, %11, %12, %13, %14, %15}, {%16, %17, %18, %19}, %20, p, 1, 1, %22;\n}\n"
    : "+r"(d[0]), "+r"(d[1]), "+r"(d[2]), "+r"(d[3]), "+r"(d[4]), "+r"(d[5]), "+r"(d[6]), "+r"(d[7]), "+r"(d[8]), "+r"(d[9]), "+r"(d[10]), "+r"(d[11]), "+r"(d[12]), "+r"(d[13]), "+r"(d[14]), "+r"(d[15])
    : "r"(a0), "r"(a1), "r"(a2), "r"(a3), "l"(db), "r"(scale_d), "n"(TB));
}
template<int TB> __device__ __forceinline__ void wgmma_hrs_n32(uint32_t (&d)[8], uint32_t a0, uint32_t a1, uint32_t a2, uint32_t a3, uint64_t db, int scale_d) {
  asm volatile("{\n.reg .pred p;\nsetp.ne.b32 p, %13, 0;\n"
    "wgmma.mma_async.sync.aligned.m64n32k16.f16.f16.f16 {%0, %1, %2, %3, %4, %5, %6, %7}, {%8, %9, %10, %11}, %12, p, 1, 1, %14;\n}\n"
    : "+r"(d[0]), "+r"(d[1]), "+r"(d[2]), "+r"(d[3]), "+r"(d[4]), "+r"(d[5]), "+r"(d[6]), "+r"(d[7])
    : "r"(a0), "r"(a1), "r"(a2), "r"(a3), "l"(db), "r"(scale_d), "n"(TB));
}

__device__ __align__(128) const uint32_t c_thr[1536] = {
  0x33fb33ff,0xa49c9de4,0x33273352,0xaf2cae76,0x33e233f1,0xa96ca7bd,0x32c432f7,0xb045afdd,0x33b733cf,0xac3eaaf7,0x3250328c,0xb0eab099,
  0x3378339a,0xadbcacff,0x31cd3211,0xb182b137,0x33d033fb,0xaadea46a,0x299e2d17,0xb3e0b396,0x32fb337a,0xafd2adb1,0xa78b1f76,0xb3f2b3ff,
  0x318b3254,0xb1c5b0e5,0xae6bac32,0xb354b3b8,0x2f4230a3,0xb321b285,0xb133b040,0xb215b2c7,0x337c33f2,0xada5a759,0xb179afc8,0xb1d6b2fe,
  0x31463293,0xb204b08e,0xb394b2ba,0xad23b055,0x2b402f4e,0xb3cbb31e,0xb3e4b3f9,0x293ba533,0xac269c52,0xb3bab400,0xb258b357,0x30e02e5f,
  0x330133e5,0xafbda922,0xb3f3b3c9,0x2727ab59,0x2deb314a,0xb36fb200,0xb194b32f,0x31bc2f0a,0xacdb2084,0xb39fb3ff,0xa565aea4,0x33f93347,
  0xb2b6b0db,0xb05ab25c,0x30892c1a,0x329733bc,0x326033d4,0xb0d6aa94,0xb00ab29b,0x32e83084,0x20e82f64,0xb3feb318,0x2d8da597,0x338133f8,
  0xb1fcae48,0xb14fb35c,0x339031b8,0x2d3a3199,0xb3e6b3ae,0x2909ac7b,0x32d133f4,0xb030a6f5,0x319d33bf,0xb1b3ac02,0x2e3ca874,0x335e33ec,
  0xacc32b89,0xb3a3b3c6,0x33f83276,0x25c930b7,0xb3dcb1f8,0xaa01b154,0x30653335,0xb2b0aef4,0xb107b383,0x32392d81,0xafa6214d,0xb307b3fe,
  0x30bc33a5,0xb273acb7,0x33c5311b,0x2ba23229,0xb0cc94b6,0xb267b400,0x30153360,0xb2e1ae31,0xb385b3ab,0x2d76ac93,0xb166a691,0xb1e7b3f5,
  0x22deb06a,0x33fd32ac,0xb337b3da,0x2ee8aa19,0x2f853387,0xb310ad6a,0x322d33fe,0xb1162216,0xb2a9abd3,0xb06fb3c2,0xb07428a6,0xb2a5b3ea,
  0xb111b3e9,0x323128be,0xb30db3c3,0x2f90abba,0x31aa227a,0x31a633fd,0x2e25ad5e,0x33633389,0x2d6a3365,0xb387ae1a,0xa21631aa,0xb3feb1a6,
  0xb3c2af85,0xabd3b310,0xb3eab22d,0x28a6b116,0xa8beb2a9,0x33e9306f,0x2bbab074,0x33c332a5,0x33fd3111,0x227a3231,0x3389330d,0xad5e2f90,
  0x2a63333f,0xb3d7aec6,0xb2a2a1b1,0xb07ab3fe,0xb3f7b158,0x25fbb1f4,0xacb7b38b,0x33a52d52,0x2e0eb025,0x336832d8,0x340030bc,0x14b63273,
  0x323533c0,0xb10c2beb,0xac9330cc,0xb3abb267,0x23433316,0xb3fdaf6f,0xb38eb225,0x2d46b11f,0xb342b29e,0x2ebbb07f,0x31e3aa7c,0x316b33d6,
  0x3264a6c3,0x30d133f5,0x2c0233ac,0xb3bfac87,0x28f0336a,0xb3e7ae02,0xb3c6b19d,0x2b89b1b3,0xa59732e8,0xb3f8b00a,0xaccfb3ed,0x33a1285b,
  0xb1b8b381,0x3199ad8d,0x336c31df,0xadf73170,0x33f42d3a,0x26f53390,0xb30423a7,0xafb2b3fc,0xb05f3030,0xb2b3b2d1,0x29e8b27a,0x33dd30b2,
  0xab5932b6,0xb3c9b05a,0x30adb089,0x327e3297,0xaf0ab3f3,0x332fa727,0x240633b0,0xb3fcac6f,0x33473194,0xaea431bc,0xb174b359,0x31daae54,
  0xb3bca565,0xac1ab3f9,0x33ee2f59,0xa842331b,0xaddf3281,0xb371b0a8,0x34002b40,0x1c5233cb,0xa759b3ef,0x33f22829,0xb2fe2c26,0xafc8b3ba,
  0x308e337c,0xb2932da5,0x3055b179,0x32ba31d6,0xb31eb146,0x2f4eb204,0xa5333394,0xb3f9ad23,0xaff33249,0xb2f1b0f3,0x30e532fb,0xb2542fd2,
  0x2b28b373,0x33cc2dd4,0xb285b18b,0x30a3b1c5,0x246a33fa,0xb3fba500,0x33962f42,0xad173321,0xadb1b3d0,0x337aaade,0xb3ffa99e,0x1f76b3e0,
  0xb0ee320d,0xb24db13c,0xac4b3398,0xb3b5ad0b,0x304ab289,0x32c1309e,0x2985b3ce,0x33e12b0f,0xaf3732f4,0xb324afe8,0xa4ce33f0,0xb3faa7ef,
  0x2dc8b34f,0x33762e82,0x9de4b3ff,0x33ff1ead,0xb1c931cd,0xb186b182,0xb3762e82,0xadc8b34f,0x324db13c,0x30ee320d,0x33b5ad0b,0x2c4b3398,
  0xb2c1309e,0xb04ab289,0xb3e12b0f,0xa985b3ce,0x3324afe8,0x2f3732f4,0x33faa7ef,0x24ce33f0,0xb285318b,0xb0a3b1c5,0xb2c7ae6b,0x3040b354,
  0x3396af42,0x2d173321,0x31413133,0xb2093215,0xb3ff299e,0x9f76b3e0,0xae8db2bd,0x334cb050,0x33b8278b,0xac3233f2,0x281033b3,0xb3ef2c57,
  0xb31e3146,0xaf4eb204,0xa533b394,0x33f9ad23,0x3400ab40,0x9c5233cb,0xae5f33e4,0xb357a93b,0xb2feac26,0x2fc8b3ba,0x3245b258,0x30f830e0,
  0x30553179,0xb2ba31d6,0xb3df2e99,0xa9b6b34a,0xb39230fd,0xad2fb241,0x3200b301,0x314a2fbd,0x337f1b11,0xad993400,0xb3ff2deb,0xa084b36f,
  0xb005b129,0x32ebb21d,0x325c2cdb,0xb0db339f,0xa92233de,0xb3e529cf,0xab59b2b6,0x33c9b05a,0xb3dd30b2,0xa9e8b27a,0x33d4ab71,0xaa9433c8,
  0x32212c0e,0xb12433bd,0xaf64b0d6,0x3318b260,0x197fb345,0x3400aeaf,0xae4833fe,0xb35c20e8,0xb23d3332,0xb102aeff,0x33aeb14f,0x2c7b31fc,
  0xb3fe3065,0xa14db2b0,0x2ebb307f,0xb342329e,0x300f2fa6,0xb2e53307,0x30d1b3f5,0x326426c3,0x302ab400,0x32d517db,0xb3e72e02,0x28f0b36a,
  0xb3fd2f6f,0x2343b316,0x2d46311f,0xb38e3225,0xb3f53015,0x2691b2e1,0xaf9b33eb,0xb30a288d,0x2a193166,0xb3da31e7,0x33d7aec6,0xaa63333f,
  0x3313b337,0x2f7a2ee8,0xa5fbb1f4,0x33f7b158,0xb1a1a8d7,0x31afb3e8,0xb36832d8,0xae0eb025,0xb3c22f85,0x2bd3b310,0xb3ea322d,0xa8a6b116,
  0xa8be32a9,0xb3e9306f,0x2bba3074,0xb3c332a5,0x33fdb111,0xa27a3231,0x3389b30d,0x2d5e2f90,0xa216b1aa,0x33feb1a6,0xaed2ae25,0x333db363,
  0xb3652edd,0x2e1ab33a,0xb1aa227a,0x31a6b3fd,0xaf853387,0xb3102d6a,0xb22d33fe,0xb116a216,0x32a9abd3,0xb06f33c2,0x307428a6,0xb2a533ea,
  0x3111b3e9,0x3231a8be,0x330db3c3,0x2f902bba,0xb2e12e31,0x3015b360,0x288db1a1,0x33ebb1af,0xb1e733f5,0xb1662691,0xb33f2f9b,0x2ec6b30a,
  0x2ee82a19,0xb33733da,0xb15833d7,0xb1f42a63,0x33e8b313,0x28d72f7a,0x302525fb,0xb2d833f7,0xb2392d81,0x3107b383,0x3307b3fe,0x2fa6214d,
  0xb35e33ec,0xae3ca874,0x97dbb00f,0x3400b2e5,0xa5c930b7,0xb3f83276,0xb316302a,0x2f6fb2d5,0x32b0aef4,0xb0653335,0xb29e33fd,0xb07f2343,
  0xb1702ccf,0x31dfb3a1,0x3345b124,0xaeaf3221,0xb3fc336c,0xa3a7adf7,0x3332b400,0x2eff997f,0xb0b23304,0xb27a2fb2,0x2b71b102,0x33c8b23d,
  0x2c0e29e8,0xb3bd33dd,0xb0d62a94,0x3260b3d4,0xb0892c1a,0x3297b3bc,0x2aad2842,0xb3d333ee,0xb3b0327e,0x2c6fb0ad,0x3241b035,0xb0fd32ce,
  0xb35933fc,0xae542406,0x3400b392,0x1b112d2f,0xaf5931da,0xb31b3174,0x321db37f,0x3129ad99,0xaf152ac6,0x332cb3d2,0xb1463293,0xb204308e,
  0xb281312e,0x30a8b219,0xab402f4e,0xb3cb331e,0xb3ef3371,0x2829addf,0x2c269c52,0xb3ba3400,0xb37c33f2,0xada52759,0x3179afc8,0xb1d632fe,
  0xacf32953,0x339cb3e3,0xb3fa33cc,0x2500ab28,0xb0942f21,0x3290b32a,0xb3d033fb,0xaade246a,0xb249317d,0x30f3b1d2,0xb2fb337a,0xafd22db1,
  0xb37332f1,0x2dd4aff3,0xb18b3254,0xb1c530e5,0xa96c27bd,0x33e2b3f1,0xb0452fdd,0x32c4b2f7,0xac3e2af7,0x33b7b3cf,0xb0ea3099,0x3250b28c,
  0xadbc2cff,0x3378b39a,0xb1823137,0x31cdb211,0xaf2c2e76,0x3327b352,0xb20d31c9,0x313cb186,0x313c3186,0xb20db1c9,0x2d0b2dc8,0xb398b376,
  0x309e30ee,0xb289b24d,0x2b0f2c4b,0xb3ceb3b5,0x2fe8304a,0xb2f4b2c1,0x27ef2985,0xb3f0b3e1,0x2e822f37,0xb34fb324,0x1ead24ce,0xb3ffb3fa,
  0xb2bdb209,0xb050b141,0xb290b32a,0x30942f21,0xb3b3b34c,0xac57ae8d,0xb0f3b1d2,0x3249317d,0xb400b3ef,0x1d1ba810,0xadd4aff3,0x337332f1,
  0xb39cb3e3,0x2cf32953,0xa500ab28,0x33fa33cc,0xae99b0f8,0x334a3245,0x33ff33b2,0x201f2c63,0x2438a9b6,0x33fc33df,0x332c33d2,0xaf15aac6,
  0x303a2ce7,0x32cb339e,0x30a83219,0xb281b12e,0x32ee31c0,0x2ffe3190,0x28292ddf,0xb3efb371,0x33b0327e,0x2c6f30ad,0xb241b035,0xb0fdb2ce,
  0x335933fc,0xae54a406,0xb400b392,0x1b11ad2f,0x2f5931da,0xb31bb174,0xb21db37f,0x31292d99,0xaaad2842,0xb3d3b3ee,0xa9cfb005,0x33de32eb,
  0x285b305f,0xb3edb2b3,0x2c0ea9e8,0x33bd33dd,0xb170accf,0xb1dfb3a1,0x33453124,0x2eaf3221,0xb3fcb36c,0x23a7adf7,0x33323400,0xaeff997f,
  0xb0b2b304,0x327a2fb2,0x2b713102,0xb3c8b23d,0xb400b2e5,0x17dbb00f,0x2e023264,0xb36ab0d1,0xaf6fb2d5,0x3316302a,0xb11fa8f0,0xb225b3e7,
  0x307f2343,0x329e33fd,0xb3d6b38e,0x2a7cad46,0x33f53342,0xa6c32ebb,0xac87b1e3,0x33ac316b,0x28d7af7a,0x33e83313,0xb2d8b3f7,0x3025a5fb,
  0x33eb31af,0x288d31a1,0x2bebae0e,0x33c03368,0x2ec6330a,0xb33faf9b,0x33fe3235,0x21b1310c,0xb1f4aa63,0xb158b3d7,0x2d5232a2,0xb38bb07a,
  0x33a7333d,0xacab2ed2,0x33f63162,0x262d31eb,0xaa4b301a,0xb3d8b2de,0x2a32326b,0xb3d9b0c7,0xb3f6b26f,0x265fb0c1,0xb3a9b020,0xac9fb2db,
  0x0e48b15d,0x340031f0,0xae1ab33a,0x33652edd,0xaed22e25,0xb33db363,0xb1eb0e48,0xb162b400,0xb2deb3a7,0x301aacab,0xb0c7b3f6,0x326b262d,
  0x30c1aa4b,0x326f33d8,0x32db2a32,0x302033d9,0x31f033f6,0xb15d265f,0x2edd33a9,0xb33aac9f,0xb2acb385,0x306aad76,0x2a19b166,0x33da31e7,
  0x3229a2de,0x311b33fd,0x33133337,0xaf7a2ee8,0x2e3133c5,0xb360aba2,0xb1a128d7,0xb1afb3e8,0xb3f5b015,0xa691b2e1,0xaf9bb3eb,0x330a288d,
  0x3154acc3,0x31f833a3,0x2ef433f8,0xb335a5c9,0x2d8133dc,0xb383aa01,0xb3feb065,0x214db2b0,0xb3ecb107,0x2874b239,0x300fafa6,0x32e53307,
  0x30b7ae3c,0x3276335e,0x302a3400,0xb2d517db,0x312433bd,0xb2212c0e,0xb318b260,0x2f64b0d6,0xb400aeaf,0x997fb345,0x335c20e8,0x2e4833fe,
  0x3102aeff,0x323d3332,0xac7b31fc,0xb3aeb14f,0x2a9433c8,0xb3d4ab71,0xb084b3e6,0x329ba909,0xb2ce2aad,0xb035b3d3,0x33e529cf,0x292233de,
  0x2d2fb241,0x339230fd,0xb14a2fbd,0xb200b301,0x2d993400,0xb37f1b11,0x2084b36f,0x33ff2deb,0xb2ebb21d,0x3005b129,0x30db339f,0xb25c2cdb,
  0xae5fb3e4,0x3357a93b,0xb190303a,0xb1c0b2cb,0x32453258,0xb0f830e0,0x2c63b2ee,0x33b22ffe,0xb3dfae99,0x29b6b34a,0x2ac633ff,0xb3d2a01f,
  0x339ea438,0x2ce733fc,0xb12eb32c,0x3219af15,0x33b8a78b,0x2c3233f2,0x2810b3b3,0x33ef2c57,0xb2c72e6b,0xb040b354,0x29533400,0xb3e31d1b,
  0x3141b133,0x32093215,0xaf21b39c,0x332aacf3,0xae8d32bd,0xb34cb050,0x317d3290,0xb1d23094,0x27bd33fb,0xb3f1249c,0x2fdd3327,0xb2f72f2c,
  0xaaf7b3e2,0x33cfa96c,0xb099b2c4,0x328cb045,0x2cff33b7,0xb39a2c3e,0x31373250,0xb21130ea,0xae76b378,0x3352adbc,0xb1c9b1cd,0x3186b182,
  0xb3ff1ead,0x1de4b3ff,0xb352adbc,0x2e76b378,0x33f1249c,0xa7bd33fb,0x32f72f2c,0xafdd3327,0xb3cfa96c,0x2af7b3e2,0xb28cb045,0x3099b2c4,
  0x339a2c3e,0xacff33b7,0x321130ea,0xb1373250,0x2953b400,0x33e31d1b,0x33ccadd4,0x2b283373,0xaf21339c,0xb32aacf3,0xb3fb2500,0x246ab3fa,
  0x317db290,0x31d23094,0x337a2ade,0xadb133d0,0xb2f130f3,0xaff3b249,0xb254afd2,0x30e5b2fb,0x339e2438,0xace733fc,0xb12e332c,0xb219af15,
  0xb190b03a,0x31c0b2cb,0x3371b0a8,0x2ddf3281,0x2c6332ee,0xb3b22ffe,0xb3f22829,0x2759b3ef,0x2ac6b3ff,0x33d2a01f,0x32932da5,0xb08e337c,
  0xaf0a33f3,0xb32fa727,0x2406b3b0,0x33fcac6f,0x3347b194,0x2ea431bc,0xb1743359,0xb1daae54,0xb3bc2565,0x2c1ab3f9,0x33eeaf59,0x2842331b,
  0x30ad3089,0xb27e3297,0xb2ceaaad,0x3035b3d3,0xb29ba909,0x3084b3e6,0x305f3030,0xb2b332d1,0x259732e8,0xb3f8300a,0x2ccfb3ed,0x33a1a85b,
  0x31b8b381,0x31992d8d,0xb36c31df,0xadf7b170,0xb3f42d3a,0x26f5b390,0x330423a7,0xafb233fc,0x316bb3d6,0x31e32a7c,0xb3832a01,0x2d81b3dc,
  0xb3bf2c87,0x2c02b3ac,0x28743239,0xb3ec3107,0x2b8931b3,0xb3c6319d,0x3276b35e,0x30b72e3c,0x31f8b3a3,0x31542cc3,0xb33525c9,0x2ef4b3f8,
  0x310c2beb,0xb23533c0,0x33abb267,0x2c9330cc,0x307ab3fe,0x32a2a1b1,0xb06aad76,0x32acb385,0xb3a52d52,0x2cb7b38b,0xb11b33fd,0xb229a2de,
  0x94b63273,0xb40030bc,0x3360aba2,0xae3133c5,0xb2de33a7,0xb01aacab,0xb0c733f6,0xb26b262d,0x30c12a4b,0xb26f33d8,0x32dbaa32,0xb02033d9,
  0x31f0b3f6,0x315d265f,0x2eddb3a9,0x333aac9f,0xb1eb8e48,0x3162b400,0xb3872e1a,0x2d6ab365,0xae25ad5e,0x3363b389,0x8e48b15d,0x3400b1f0,
  0xb3a7333d,0xacabaed2,0xb3f63162,0x262db1eb,0x2a4b301a,0xb3d832de,0xaa32326b,0xb3d930c7,0x33f6b26f,0x265f30c1,0x33a9b020,0xac9f32db,
  0x33c0b368,0x2beb2e0e,0x30cc94b6,0xb2673400,0x21b1b10c,0x33feb235,0x3385b3ab,0x2d762c93,0xb38b307a,0x2d52b2a2,0xa2deb06a,0x33fdb2ac,
  0xb0bc33a5,0xb2732cb7,0xb3c5311b,0x2ba2b229,0x26c32ebb,0xb3f53342,0xb3ac316b,0x2c87b1e3,0x336ab0d1,0xae023264,0xb19d33bf,0xb1b32c02,
  0x3225b3e7,0x311fa8f0,0x2cc32b89,0xb3a333c6,0xaa7cad46,0x33d6b38e,0x33dcb1f8,0xaa013154,0xb3fe3318,0x20e8af64,0x3381b3f8,0x2d8d2597,
  0xb14f335c,0xb1fc2e48,0x2d3ab199,0x3390b1b8,0x29092c7b,0xb3e633ae,0xb03026f5,0x32d1b3f4,0x32e8b084,0xb00a329b,0xb3ed32b3,0x285bb05f,
  0x29cfb005,0x33deb2eb,0xb05a325c,0xb2b630db,0xafbd2922,0x3301b3e5,0x27272b59,0xb3f333c9,0xb36f3200,0x2debb14a,0x31bcaf0a,0xb194332f,
  0xb39f33ff,0xacdba084,0x33f9b347,0xa5652ea4,0x3394b2ba,0xad233055,0xa438a9b6,0x33fcb3df,0x33e4b3f9,0x293b2533,0xb03a2ce7,0x32cbb39e,
  0x3258b357,0x30e0ae5f,0xb2ee31c0,0x2ffeb190,0x2e99b0f8,0x334ab245,0xb3ff33b2,0x201fac63,0xaf4230a3,0xb3213285,0x3133b040,0xb21532c7,
  0xa99e2d17,0xb3e03396,0x32bdb209,0xb0503141,0x278b1f76,0xb3f233ff,0x33b3b34c,0xac572e8d,0x2e6bac32,0xb35433b8,0x3400b3ef,0x1d1b2810,
  0xb289324d,0x309eb0ee,0xb3ce33b5,0x2b0fac4b,0xb2f432c1,0x2fe8b04a,0xb3f033e1,0x27efa985,0xb34f3324,0x2e82af37,0xb3ff33fa,0x1eada4ce,
  0xb3983376,0x2d0badc8,0xb3fb33ff,0xa49c1de4,0x351c35f6,0xac93a617,0xb8a3b93c,0x308d2a16,0x32f43448,0xb160afa5,0xb6a4b7fe,0x353a3389,
  0x2fa53160,0xb448b2f4,0xb389b53a,0x37fe36a4,0x26172c93,0xb5f6b51c,0xaa16b08d,0x393c38a3,0x34c3358c,0xac47a5b2,0xb85fb8f3,0x304229b1,
  0x327e33fd,0xb106af26,0xb63cb785,0x34e7330f,0x2f263106,0xb3fdb27e,0xb30fb4e7,0x3785363c,0x25b22c47,0xb58cb4c3,0xa9b1b042,0x38f3385f,
  0x346a3523,0xabf6a54d,0xb81ab8a8,0x2fef294d,0x3209336b,0xb0acaea7,0xb5d4b70a,0x34933294,0x2ea730ac,0xb36bb209,0xb294b493,0x370a35d4,
  0x254d2bf6,0xb523b46a,0xa94dafef,0x38a8381a,0x341334bc,0xab5fa4e9,0xb7a6b85a,0x2f5928e8,0x319432da,0xb052ae28,0xb56ab68d,0x343e3219,
  0x2e283052,0xb2dab194,0xb219b43e,0x368d356a,0x24e92b5f,0xb4bcb413,0xa8e8af59,0x385a37a6,0x33783456,0xaac8a484,0xb715b80a,0x2ec32884,
  0x3120324a,0xaff2ada9,0xb4ffb60e,0x33d3319e,0x2da92ff2,0xb24ab120,0xb19eb3d3,0x360e34ff,0x24842ac8,0xb456b378,0xa884aec3,0x380a3715,
  0x32cd33e3,0xaa31a420,0xb682b76f,0x2e2d281f,0x30ac31bb,0xaf3fad2a,0xb493b58d,0x33283122,0x2d2a2f3f,0xb1bbb0ac,0xb122b328,0x358d3493,
  0x24202a31,0xb3e3b2cd,0xa81fae2d,0x376f3682,0x3223331c,0xa999a376,0xb5ebb6c6,0x2d972776,0x3039312d,0xae8dacac,0xb426b50b,0x327c30a6,
  0x2cac2e8d,0xb12db039,0xb0a6b27c,0x350b3426,0x23762999,0xb31cb223,0xa776ad97,0x36c635eb,0x317a3257,0xa902a2ad,0xb552b61a,0x2d0026ad,
  0x2f8c309f,0xaddcac2e,0xb371b487,0x31cf3029,0x2c2e2ddc,0xb09faf8c,0xb029b1cf,0x34873371,0x22ad2902,0xb257b17a,0xa6adad00,0x361a3552,
  0x30d23194,0xa86ba1e4,0xb4b7b56a,0x2c6a25e4,0x2ea73012,0xad2aab5f,0xb294b402,0x31222f59,0x2b5f2d2a,0xb012aea7,0xaf59b122,0x34023294,
  0x21e4286b,0xb194b0d2,0xa5e4ac6a,0x356a34b7,0x302c30d2,0xa7a9a11b,0xb41ab4b7,0x2ba7251b,0x2dc22f0c,0xac79aa63,0xb1b6b2f7,0x30742e5f,
  0x2a632c79,0xaf0cadc2,0xae5fb074,0x32f731b6,0x211b27a9,0xb0d2b02c,0xa51baba7,0x34b7341a,0x2f0c3012,0xa67ba052,0xb2f7b402,0x2a7a2452,
  0x2cde2df5,0xab91a967,0xb0d7b1e8,0x2f8b2d65,0x29672b91,0xadf5acde,0xad65af8b,0x31e830d7,0x2052267b,0xb012af0c,0xa452aa7a,0x340232f7,
  0x2dc22ea7,0xa54d9f12,0xb1b6b294,0x294d2311,0x2bf62cde,0xaa31a86b,0xafefb0d7,0x2e2d2c6a,0x286b2a31,0xacdeabf6,0xac6aae2d,0x30d72fef,
  0x1f12254d,0xaea7adc2,0xa311a94d,0x329431b6,0x2c792d2a,0xa4209d7f,0xb074b122,0x281f217f,0x2a312b91,0xa8d0a6e0,0xae2daf8b,0x2cce2ade,
  0x26e028d0,0xab91aa31,0xaadeacce,0x2f8b2e2d,0x1d7f2420,0xad2aac79,0xa17fa81f,0x31223074,0x2a632b5f,0xa1e49bdb,0xae5faf59,0x25e41fdb,
  0x286b2967,0xa6e0a4e9,0xac6aad65,0x2ade28e8,0x24e926e0,0xa967a86b,0xa8e8aade,0x2d652c6a,0x1bdb21e4,0xab5faa63,0x9fdba5e4,0x2f592e5f,
  0x27a9286b,0x9f1298b6,0xaba7ac6a,0x23111cb6,0x254d267b,0xa420a1e4,0xa94daa7a,0x281f25e4,0x21e42420,0xa67ba54d,0xa5e4a81f,0x2a7a294d,
  0x18b61f12,0xa86ba7a9,0x9cb6a311,0x2c6a2ba7,0x211b21e4,0x98b69248,0xa51ba5e4,0x1cb61648,0x1f122052,0x9d7f9bdb,0xa311a452,0x217f1fdb,
  0x1bdb1d7f,0xa0529f12,0x9fdba17f,0x24522311,0x124818b6,0xa1e4a11b,0x96489cb6,0x25e4251b,0xa11ba1e4,0x18b61248,0x251b25e4,0x9cb69648,
  0x9f12a052,0x1d7f1bdb,0x23112452,0xa17f9fdb,0x9bdb9d7f,0x20521f12,0x1fdb217f,0xa452a311,0x924898b6,0x21e4211b,0x16481cb6,0xa5e4a51b,
  0xa7a9a86b,0x1f1218b6,0x2ba72c6a,0xa3119cb6,0xa54da67b,0x242021e4,0x294d2a7a,0xa81fa5e4,0xa1e4a420,0x267b254d,0x25e4281f,0xaa7aa94d,
  0x98b69f12,0x286b27a9,0x1cb62311,0xac6aaba7,0xaa63ab5f,0x21e41bdb,0x2e5f2f59,0xa5e49fdb,0xa86ba967,0x26e024e9,0x2c6a2d65,0xaadea8e8,
  0xa4e9a6e0,0x2967286b,0x28e82ade,0xad65ac6a,0x9bdba1e4,0x2b5f2a63,0x1fdb25e4,0xaf59ae5f,0xac79ad2a,0x24201d7f,0x30743122,0xa81fa17f,
  0xaa31ab91,0x28d026e0,0x2e2d2f8b,0xacceaade,0xa6e0a8d0,0x2b912a31,0x2ade2cce,0xaf8bae2d,0x9d7fa420,0x2d2a2c79,0x217f281f,0xb122b074,
  0xadc2aea7,0x254d1f12,0x31b63294,0xa94da311,0xabf6acde,0x2a31286b,0x2fef30d7,0xae2dac6a,0xa86baa31,0x2cde2bf6,0x2c6a2e2d,0xb0d7afef,
  0x9f12a54d,0x2ea72dc2,0x2311294d,0xb294b1b6,0xaf0cb012,0x267b2052,0x32f73402,0xaa7aa452,0xacdeadf5,0x2b912967,0x30d731e8,0xaf8bad65,
  0xa967ab91,0x2df52cde,0x2d652f8b,0xb1e8b0d7,0xa052a67b,0x30122f0c,0x24522a7a,0xb402b2f7,0xb02cb0d2,0x27a9211b,0x341a34b7,0xaba7a51b,
  0xadc2af0c,0x2c792a63,0x31b632f7,0xb074ae5f,0xaa63ac79,0x2f0c2dc2,0x2e5f3074,0xb2f7b1b6,0xa11ba7a9,0x30d2302c,0x251b2ba7,0xb4b7b41a,
  0xb0d2b194,0x286b21e4,0x34b7356a,0xac6aa5e4,0xaea7b012,0x2d2a2b5f,0x32943402,0xb122af59,0xab5fad2a,0x30122ea7,0x2f593122,0xb402b294,
  0xa1e4a86b,0x319430d2,0x25e42c6a,0xb56ab4b7,0xb17ab257,0x290222ad,0x3552361a,0xad00a6ad,0xaf8cb09f,0x2ddc2c2e,0x33713487,0xb1cfb029,
  0xac2eaddc,0x309f2f8c,0x302931cf,0xb487b371,0xa2ada902,0x3257317a,0x26ad2d00,0xb61ab552,0xb223b31c,0x29992376,0x35eb36c6,0xad97a776,
  0xb039b12d,0x2e8d2cac,0x3426350b,0xb27cb0a6,0xacacae8d,0x312d3039,0x30a6327c,0xb50bb426,0xa376a999,0x331c3223,0x27762d97,0xb6c6b5eb,
  0xb2cdb3e3,0x2a312420,0x3682376f,0xae2da81f,0xb0acb1bb,0x2f3f2d2a,0x3493358d,0xb328b122,0xad2aaf3f,0x31bb30ac,0x31223328,0xb58db493,
  0xa420aa31,0x33e332cd,0x281f2e2d,0xb76fb682,0xb378b456,0x2ac82484,0x3715380a,0xaec3a884,0xb120b24a,0x2ff22da9,0x34ff360e,0xb3d3b19e,
  0xada9aff2,0x324a3120,0x319e33d3,0xb60eb4ff,0xa484aac8,0x34563378,0x28842ec3,0xb80ab715,0xb413b4bc,0x2b5f24e9,0x37a6385a,0xaf59a8e8,
  0xb194b2da,0x30522e28,0x356a368d,0xb43eb219,0xae28b052,0x32da3194,0x3219343e,0xb68db56a,0xa4e9ab5f,0x34bc3413,0x28e82f59,0xb85ab7a6,
  0xb46ab523,0x2bf6254d,0x381a38a8,0xafefa94d,0xb209b36b,0x30ac2ea7,0x35d4370a,0xb493b294,0xaea7b0ac,0x336b3209,0x32943493,0xb70ab5d4,
  0xa54dabf6,0x3523346a,0x294d2fef,0xb8a8b81a,0xb4c3b58c,0x2c4725b2,0x385f38f3,0xb042a9b1,0xb27eb3fd,0x31062f26,0x363c3785,0xb4e7b30f,
  0xaf26b106,0x33fd327e,0x330f34e7,0xb785b63c,0xa5b2ac47,0x358c34c3,0x29b13042,0xb8f3b85f,0xb51cb5f6,0x2c932617,0x38a3393c,0xb08daa16,
  0xb2f4b448,0x31602fa5,0x36a437fe,0xb53ab389,0xafa5b160,0x344832f4,0x3389353a,0xb7feb6a4,0xa617ac93,0x35f6351c,0x2a16308d,0xb93cb8a3,
};
__device__ __align__(128) const uint32_t c_img[2560] = {
  0x326d31ed,0x333b32dd,0x33c33388,0x33fe33ea,0x33c331ed,0x31ed33c3,0xa8b22d64,0xb33bb0c4,0x33ea31ed,0xad64301d,0xb2ddb388,0x315fa8b2,
  0x32dd31ed,0xb3feabc6,0x326dad64,0xad64326d,0x30c431ed,0xaed7b2dd,0x2bc63388,0xa248b3ea,0x2bc631ed,0x315fb3c3,0xb3ea2d64,0x2ed730c4,
  0xa8b231ed,0x3388b01d,0x301db388,0xb1ed28b2,0xb01d31ed,0x22482bc6,0x30c4ad64,0x3388b26d,0x33ea33fe,0x338833c3,0x32dd333b,0x31ed326d,
  0xb2ddb3fe,0xa248b01d,0x326d2ed7,0x338833ea,0x30c433fe,0xb33babc6,0xabc6b33b,0x33fe30c4,0xabc6b3fe,0x31ed32dd,0xb3eaaed7,0x333ba8b2,
  0xa8b233fe,0x2d64b3c3,0xb01d333b,0x315fb26d,0x301db3fe,0xb3fe301d,0x30c42ed7,0x2d64b3ea,0xb26d33fe,0x2ed72bc6,0x33c3b33b,0xa248b0c4,
  0x33c3b3fe,0x315fb2dd,0x28b2aed7,0xaed728b2,0xb0c4b15f,0xaed7b01d,0xabc6ad64,0xa248a8b2,0xabc6b15f,0x315f2bc6,0x33ea3388,0x2ed7326d,
  0x28b2b15f,0x338832dd,0xb01d2d64,0xb1edb3ea,0x301db15f,0x224833c3,0xb0c4b388,0x338830c4,0x326db15f,0xb33b301d,0x33c3ad64,0xb3fe28b2,
  0x33c3b15f,0xb1edabc6,0xa8b23388,0x333bb26d,0x33eab15f,0x2d64b2dd,0xb2dd2d64,0xb15f33ea,0x32ddb15f,0x33feb3c3,0x326db388,0x2d64b0c4,
  0x28b22248,0x2d642bc6,0x301d2ed7,0x315f30c4,0xb01da248,0xb3feb2dd,0xb0c4b33b,0x2d64a8b2,0x326d2248,0x2ed733c3,0xb3c3aed7,0xa248b26d,
  0xb3c3a248,0x315fb01d,0xa8b2333b,0xaed7b3ea,0x33ea2248,0xb388abc6,0x32dd2ed7,0xb1edb0c4,0xb2dda248,0x224832dd,0x326db33b,0xb38828b2,
  0x30c42248,0x333bb3c3,0xabc6aed7,0xb3fe326d,0xabc6a248,0xb1ed301d,0xb3ea333b,0xb33b33ea,0xb26d31ed,0xb33b32dd,0xb3c33388,0xb3fe33ea,
  0xb3c331ed,0xb1ed33c3,0x28b22d64,0x333bb0c4,0xb3ea31ed,0x2d64301d,0x32ddb388,0xb15fa8b2,0xb2dd31ed,0x33feabc6,0xb26dad64,0x2d64326d,
  0xb0c431ed,0x2ed7b2dd,0xabc63388,0x2248b3ea,0xabc631ed,0xb15fb3c3,0x33ea2d64,0xaed730c4,0x28b231ed,0xb388b01d,0xb01db388,0x31ed28b2,
  0x301d31ed,0xa2482bc6,0xb0c4ad64,0xb388b26d,0xb3ea33fe,0xb38833c3,0xb2dd333b,0xb1ed326d,0x32ddb3fe,0x2248b01d,0xb26d2ed7,0xb38833ea,
  0xb0c433fe,0x333babc6,0x2bc6b33b,0xb3fe30c4,0x2bc6b3fe,0xb1ed32dd,0x33eaaed7,0xb33ba8b2,0x28b233fe,0xad64b3c3,0x301d333b,0xb15fb26d,
  0xb01db3fe,0x33fe301d,0xb0c42ed7,0xad64b3ea,0x326d33fe,0xaed72bc6,0xb3c3b33b,0x2248b0c4,0xb3c3b3fe,0xb15fb2dd,0xa8b2aed7,0x2ed728b2,
  0x30c4b15f,0x2ed7b01d,0x2bc6ad64,0x2248a8b2,0x2bc6b15f,0xb15f2bc6,0xb3ea3388,0xaed7326d,0xa8b2b15f,0xb38832dd,0x301d2d64,0x31edb3ea,
  0xb01db15f,0xa24833c3,0x30c4b388,0xb38830c4,0xb26db15f,0x333b301d,0xb3c3ad64,0x33fe28b2,0xb3c3b15f,0x31edabc6,0x28b23388,0xb33bb26d,
  0xb3eab15f,0xad64b2dd,0x32dd2d64,0x315f33ea,0xb2ddb15f,0xb3feb3c3,0xb26db388,0xad64b0c4,0xa8b22248,0xad642bc6,0xb01d2ed7,0xb15f30c4,
  0x301da248,0x33feb2dd,0x30c4b33b,0xad64a8b2,0xb26d2248,0xaed733c3,0x33c3aed7,0x2248b26d,0x33c3a248,0xb15fb01d,0x28b2333b,0x2ed7b3ea,
  0xb3ea2248,0x3388abc6,0xb2dd2ed7,0x31edb0c4,0x32dda248,0xa24832dd,0xb26db33b,0x338828b2,0xb0c42248,0xb33bb3c3,0x2bc6aed7,0x33fe326d,
  0x2bc6a248,0x31ed301d,0x33ea333b,0x333b33ea,0x30c4315f,0x2ed7301d,0x2bc62d64,0x224828b2,0x2bc6315f,0xb15fabc6,0xb3eab388,0xaed7b26d,
  0xa8b2315f,0xb388b2dd,0x301dad64,0x31ed33ea,0xb01d315f,0xa248b3c3,0x30c43388,0xb388b0c4,0xb26d315f,0x333bb01d,0xb3c32d64,0x33fea8b2,
  0xb3c3315f,0x31ed2bc6,0x28b2b388,0xb33b326d,0xb3ea315f,0xad6432dd,0x32ddad64,0x315fb3ea,0xb2dd315f,0xb3fe33c3,0xb26d3388,0xad6430c4,
  0xa8b2a248,0xad64abc6,0xb01daed7,0xb15fb0c4,0x301d2248,0x33fe32dd,0x30c4333b,0xad6428b2,0xb26da248,0xaed7b3c3,0x33c32ed7,0x2248326d,
  0x33c32248,0xb15f301d,0x28b2b33b,0x2ed733ea,0xb3eaa248,0x33882bc6,0xb2ddaed7,0x31ed30c4,0x32dd2248,0xa248b2dd,0xb26d333b,0x3388a8b2,
  0xb0c4a248,0xb33b33c3,0x2bc62ed7,0x33feb26d,0x2bc62248,0x31edb01d,0x33eab33b,0x333bb3ea,0x326d31ed,0x333b32dd,0x33c33388,0x33fe33ea,
  0x33c331ed,0x31ed33c3,0xa8b22d64,0xb33bb0c4,0x33ea31ed,0xad64301d,0xb2ddb388,0x315fa8b2,0x32dd31ed,0xb3feabc6,0x326dad64,0xad64326d,
  0x30c431ed,0xaed7b2dd,0x2bc63388,0xa248b3ea,0x2bc631ed,0x315fb3c3,0xb3ea2d64,0x2ed730c4,0xa8b231ed,0x3388b01d,0x301db388,0xb1ed28b2,
  0xb01d31ed,0x22482bc6,0x30c4ad64,0x3388b26d,0x33ea33fe,0x338833c3,0x32dd333b,0x31ed326d,0xb2ddb3fe,0xa248b01d,0x326d2ed7,0x338833ea,
  0x30c433fe,0xb33babc6,0xabc6b33b,0x33fe30c4,0xabc6b3fe,0x31ed32dd,0xb3eaaed7,0x333ba8b2,0xa8b233fe,0x2d64b3c3,0xb01d333b,0x315fb26d,
  0x301db3fe,0xb3fe301d,0x30c42ed7,0x2d64b3ea,0xb26d33fe,0x2ed72bc6,0x33c3b33b,0xa248b0c4,0x33c3b3fe,0x315fb2dd,0x28b2aed7,0xaed728b2,
  0xb0c4315f,0xaed7301d,0xabc62d64,0xa24828b2,0xabc6315f,0x315fabc6,0x33eab388,0x2ed7b26d,0x28b2315f,0x3388b2dd,0xb01dad64,0xb1ed33ea,
  0x301d315f,0x2248b3c3,0xb0c43388,0x3388b0c4,0x326d315f,0xb33bb01d,0x33c32d64,0xb3fea8b2,0x33c3315f,0xb1ed2bc6,0xa8b2b388,0x333b326d,
  0x33ea315f,0x2d6432dd,0xb2ddad64,0xb15fb3ea,0x32dd315f,0x33fe33c3,0x326d3388,0x2d6430c4,0x28b2a248,0x2d64abc6,0x301daed7,0x315fb0c4,
  0xb01d2248,0xb3fe32dd,0xb0c4333b,0x2d6428b2,0x326da248,0x2ed7b3c3,0xb3c32ed7,0xa248326d,0xb3c32248,0x315f301d,0xa8b2b33b,0xaed733ea,
  0x33eaa248,0xb3882bc6,0x32ddaed7,0xb1ed30c4,0xb2dd2248,0x2248b2dd,0x326d333b,0xb388a8b2,0x30c4a248,0x333b33c3,0xabc62ed7,0xb3feb26d,
  0xabc62248,0xb1edb01d,0xb3eab33b,0xb33bb3ea,0xb26d31ed,0xb33b32dd,0xb3c33388,0xb3fe33ea,0xb3c331ed,0xb1ed33c3,0x28b22d64,0x333bb0c4,
  0xb3ea31ed,0x2d64301d,0x32ddb388,0xb15fa8b2,0xb2dd31ed,0x33feabc6,0xb26dad64,0x2d64326d,0xb0c431ed,0x2ed7b2dd,0xabc63388,0x2248b3ea,
  0xabc631ed,0xb15fb3c3,0x33ea2d64,0xaed730c4,0x28b231ed,0xb388b01d,0xb01db388,0x31ed28b2,0x301d31ed,0xa2482bc6,0xb0c4ad64,0xb388b26d,
  0xb3ea33fe,0xb38833c3,0xb2dd333b,0xb1ed326d,0x32ddb3fe,0x2248b01d,0xb26d2ed7,0xb38833ea,0xb0c433fe,0x333babc6,0x2bc6b33b,0xb3fe30c4,
  0x2bc6b3fe,0xb1ed32dd,0x33eaaed7,0xb33ba8b2,0x28b233fe,0xad64b3c3,0x301d333b,0xb15fb26d,0xb01db3fe,0x33fe301d,0xb0c42ed7,0xad64b3ea,
  0x326d33fe,0xaed72bc6,0xb3c3b33b,0x2248b0c4,0xb3c3b3fe,0xb15fb2dd,0xa8b2aed7,0x2ed728b2,0x29ed29ed,0x29ed29ed,0x29ed29ed,0x29ed29ed,
  0x2bc32a6d,0x2add2bea,0x23c628c4,0xa81da0b2,0x2bc32add,0xa3c6281d,0xabc3aadd,0x23c6a81d,0x29ed2b3b,0xabfea564,0x295fa6d7,0x1a482b88,
  0x25642b88,0xa564ab88,0x25642b88,0xa564ab88,0xa0b22bc3,0x2a6daadd,0xabea23c6,0x28c4281d,0xa8c42bea,0x2a6da0b2,0x28c4abea,0xaa6d20b2,
  0xab3b2bfe,0xa564295f,0x26d79a48,0x2b88a9ed,0x29ed29ed,0x29ed29ed,0x29ed29ed,0x29ed29ed,0xabc3aa6d,0xaaddabea,0xa3c6a8c4,0x281d20b2,
  0x2bc32add,0xa3c6281d,0xabc3aadd,0x23c6a81d,0xa9edab3b,0x2bfe2564,0xa95f26d7,0x9a48ab88,0x25642b88,0xa564ab88,0x25642b88,0xa564ab88,
  0x20b2abc3,0xaa6d2add,0x2beaa3c6,0xa8c4a81d,0xa8c42bea,0x2a6da0b2,0x28c4abea,0xaa6d20b2,0x2b3babfe,0x2564a95f,0xa6d71a48,0xab8829ed,
  0x295f295f,0x295f295f,0x295f295f,0x295f295f,0x23c628c4,0xa81da0b2,0xabc3aa6d,0xaaddabea,0xa3c6281d,0xabc3aadd,0x23c6a81d,0x2bc32add,
  0xa95f26d7,0x9a48ab88,0x29ed2b3b,0xabfea564,0xab882564,0x2b88a564,0xab882564,0x2b88a564,0xabea23c6,0x28c4281d,0x20b2abc3,0xaa6d2add,
  0xaa6d20b2,0xa8c42bea,0x2a6da0b2,0x28c4abea,0xa6d71a48,0xab8829ed,0xab3b2bfe,0xa564295f,0x295f295f,0x295f295f,0x295f295f,0x295f295f,
  0xa3c6a8c4,0x281d20b2,0x2bc32a6d,0x2add2bea,0xa3c6281d,0xabc3aadd,0x23c6a81d,0x2bc32add,0x295fa6d7,0x1a482b88,0xa9edab3b,0x2bfe2564,
  0xab882564,0x2b88a564,0xab882564,0x2b88a564,0x2beaa3c6,0xa8c4a81d,0xa0b22bc3,0x2a6daadd,0xaa6d20b2,0xa8c42bea,0x2a6da0b2,0x28c4abea,
  0x26d79a48,0x2b88a9ed,0x2b3babfe,0x2564a95f,0xabfe2bfe,0xabfe2bfe,0xabfe2bfe,0xabfe2bfe,0xaadd2bea,0xa3c628c4,0x281da0b2,0x2bc3aa6d,
  0xa81d2bc3,0x2adda3c6,0x281dabc3,0xaadd23c6,0x9a482b88,0x29edab3b,0xabfe2564,0x295f26d7,0x26d72b3b,0xa6d7ab3b,0x26d72b3b,0xa6d7ab3b,
  0x2a6d2add,0xabeaa3c6,0x28c4a81d,0x20b22bc3,0x2bea2a6d,0xa0b228c4,0xabeaaa6d,0x20b2a8c4,0x2b8829ed,0x2b3b2bfe,0x2564295f,0xa6d79a48,
  0xabfe2bfe,0xabfe2bfe,0xabfe2bfe,0xabfe2bfe,0x2addabea,0x23c6a8c4,0xa81d20b2,0xabc32a6d,0xa81d2bc3,0x2adda3c6,0x281dabc3,0xaadd23c6,
  0x1a48ab88,0xa9ed2b3b,0x2bfea564,0xa95fa6d7,0x26d72b3b,0xa6d7ab3b,0x26d72b3b,0xa6d7ab3b,0xaa6daadd,0x2bea23c6,0xa8c4281d,0xa0b2abc3,
  0x2bea2a6d,0xa0b228c4,0xabeaaa6d,0x20b2a8c4,0xab88a9ed,0xab3babfe,0xa564a95f,0x26d71a48,0x1a489a48,0x1a489a48,0x1a489a48,0x1a489a48,
  0x281da0b2,0x2bc3aa6d,0x2addabea,0x23c6a8c4,0x2adda3c6,0x281dabc3,0xaadd23c6,0xa81d2bc3,0x2bfea564,0xa95fa6d7,0x9a482b88,0x29edab3b,
  0x2b3ba6d7,0xab3b26d7,0x2b3ba6d7,0xab3b26d7,0x28c4a81d,0x20b22bc3,0xaa6daadd,0x2bea23c6,0x20b2a8c4,0x2bea2a6d,0xa0b228c4,0xabeaaa6d,
  0xa564a95f,0x26d71a48,0x2b8829ed,0x2b3b2bfe,0x1a489a48,0x1a489a48,0x1a489a48,0x1a489a48,0xa81d20b2,0xabc32a6d,0xaadd2bea,0xa3c628c4,
  0x2adda3c6,0x281dabc3,0xaadd23c6,0xa81d2bc3,0xabfe2564,0x295f26d7,0x1a48ab88,0xa9ed2b3b,0x2b3ba6d7,0xab3b26d7,0x2b3ba6d7,0xab3b26d7,
  0xa8c4281d,0xa0b2abc3,0x2a6d2add,0xabeaa3c6,0x20b2a8c4,0x2bea2a6d,0xa0b228c4,0xabeaaa6d,0x2564295f,0xa6d79a48,0xab88a9ed,0xab3babfe,
  0xa95fa95f,0xa95fa95f,0xa95fa95f,0xa95fa95f,0xa3c6a8c4,0x281d20b2,0x2bc32a6d,0x2add2bea,0x23c6a81d,0x2bc32add,0xa3c6281d,0xabc3aadd,
  0x295fa6d7,0x1a482b88,0xa9edab3b,0x2bfe2564,0x2b88a564,0xab882564,0x2b88a564,0xab882564,0x2beaa3c6,0xa8c4a81d,0xa0b22bc3,0x2a6daadd,
  0x2a6da0b2,0x28c4abea,0xaa6d20b2,0xa8c42bea,0x26d79a48,0x2b88a9ed,0x2b3babfe,0x2564a95f,0xa95fa95f,0xa95fa95f,0xa95fa95f,0xa95fa95f,
  0x23c628c4,0xa81da0b2,0xabc3aa6d,0xaaddabea,0x23c6a81d,0x2bc32add,0xa3c6281d,0xabc3aadd,0xa95f26d7,0x9a48ab88,0x29ed2b3b,0xabfea564,
  0x2b88a564,0xab882564,0x2b88a564,0xab882564,0xabea23c6,0x28c4281d,0x20b2abc3,0xaa6d2add,0x2a6da0b2,0x28c4abea,0xaa6d20b2,0xa8c42bea,
  0xa6d71a48,0xab8829ed,0xab3b2bfe,0xa564295f,0x29ed29ed,0x29ed29ed,0x29ed29ed,0x29ed29ed,0x2bc32a6d,0x2add2bea,0x23c628c4,0xa81da0b2,
  0x2bc32add,0xa3c6281d,0xabc3aadd,0x23c6a81d,0x29ed2b3b,0xabfea564,0x295fa6d7,0x1a482b88,0x25642b88,0xa564ab88,0x25642b88,0xa564ab88,
  0xa0b22bc3,0x2a6daadd,0xabea23c6,0x28c4281d,0xa8c42bea,0x2a6da0b2,0x28c4abea,0xaa6d20b2,0xab3b2bfe,0xa564295f,0x26d79a48,0x2b88a9ed,
  0x29ed29ed,0x29ed29ed,0x29ed29ed,0x29ed29ed,0xabc3aa6d,0xaaddabea,0xa3c6a8c4,0x281d20b2,0x2bc32add,0xa3c6281d,0xabc3aadd,0x23c6a81d,
  0xa9edab3b,0x2bfe2564,0xa95f26d7,0x9a48ab88,0x25642b88,0xa564ab88,0x25642b88,0xa564ab88,0x20b2abc3,0xaa6d2add,0x2beaa3c6,0xa8c4a81d,
  0xa8c42bea,0x2a6da0b2,0x28c4abea,0xaa6d20b2,0x2b3babfe,0x2564a95f,0xa6d71a48,0xab8829ed,0x9a481a48,0x9a481a48,0x9a481a48,0x9a481a48,
  0xa81d20b2,0xabc32a6d,0xaadd2bea,0xa3c628c4,0xaadd23c6,0xa81d2bc3,0x2adda3c6,0x281dabc3,0xabfe2564,0x295f26d7,0x1a48ab88,0xa9ed2b3b,
  0xab3b26d7,0x2b3ba6d7,0xab3b26d7,0x2b3ba6d7,0xa8c4281d,0xa0b2abc3,0x2a6d2add,0xabeaa3c6,0xa0b228c4,0xabeaaa6d,0x20b2a8c4,0x2bea2a6d,
  0x2564295f,0xa6d79a48,0xab88a9ed,0xab3babfe,0x9a481a48,0x9a481a48,0x9a481a48,0x9a481a48,0x281da0b2,0x2bc3aa6d,0x2addabea,0x23c6a8c4,
  0xaadd23c6,0xa81d2bc3,0x2adda3c6,0x281dabc3,0x2bfea564,0xa95fa6d7,0x9a482b88,0x29edab3b,0xab3b26d7,0x2b3ba6d7,0xab3b26d7,0x2b3ba6d7,
  0x28c4a81d,0x20b22bc3,0xaa6daadd,0x2bea23c6,0xa0b228c4,0xabeaaa6d,0x20b2a8c4,0x2bea2a6d,0xa564a95f,0x26d71a48,0x2b8829ed,0x2b3b2bfe,
  0xabfe2bfe,0xabfe2bfe,0xabfe2bfe,0xabfe2bfe,0xaadd2bea,0xa3c628c4,0x281da0b2,0x2bc3aa6d,0xa81d2bc3,0x2adda3c6,0x281dabc3,0xaadd23c6,
  0x9a482b88,0x29edab3b,0xabfe2564,0x295f26d7,0x26d72b3b,0xa6d7ab3b,0x26d72b3b,0xa6d7ab3b,0x2a6d2add,0xabeaa3c6,0x28c4a81d,0x20b22bc3,
  0x2bea2a6d,0xa0b228c4,0xabeaaa6d,0x20b2a8c4,0x2b8829ed,0x2b3b2bfe,0x2564295f,0xa6d79a48,0xabfe2bfe,0xabfe2bfe,0xabfe2bfe,0xabfe2bfe,
  0x2addabea,0x23c6a8c4,0xa81d20b2,0xabc32a6d,0xa81d2bc3,0x2adda3c6,0x281dabc3,0xaadd23c6,0x1a48ab88,0xa9ed2b3b,0x2bfea564,0xa95fa6d7,
  0x26d72b3b,0xa6d7ab3b,0x26d72b3b,0xa6d7ab3b,0xaa6daadd,0x2bea23c6,0xa8c4281d,0xa0b2abc3,0x2bea2a6d,0xa0b228c4,0xabeaaa6d,0x20b2a8c4,
  0xab88a9ed,0xab3babfe,0xa564a95f,0x26d71a48,0x3bfb3bff,0x3be53bf2,0x3bbf3bd4,0x3b873ba5,0x3bd03bfb,0x3b013b7c,0x399d3a60,0x378538bc,
  0x35173b52,0xbbc9b7c8,0xb074ba9b,0x3bfe391b,0x319e3b27,0xbbf3b979,0x363cb80a,0x3a2d3bc5,0xba093986,0x3a7eb8f8,0xbae5385f,0x3b3db77a,
  0xbabd393c,0x3bb0b699,0xbc00305b,0x3ba730d7,0xbb2a35c8,0xb8353bb2,0x3a64b1e8,0x3962bbf7,0xba90350b,0xba413bff,0x3602340e,0x3bf6bad8,
  0xac6aa5e4,0xb122af59,0xb402b294,0xb56ab4b7,0xb2deac9c,0xb7bdb5a5,0xb9b3b8d6,0xbb10ba73,0xbb96b676,0xb359bafe,0x3bec3884,0x2a163a29,
  0xbbe0b72c,0x2f27b9d6,0x3b5e3ae8,0xb91633a2,0xb941b9c9,0x38ad3a45,0xb80fbab3,0x36d23b13,0xb850ba0d,0x346f3b4a,0x1fdbbbed,0xb4ab3be8,
  0x3721bb76,0xbace3463,0xb8d13bdd,0x39ebadfb,0x3894bb98,0xb8fd281f,0xbb6a3bbd,0x2e2d3825,0x3b3f3b65,0x3ae83b16,0x3a813ab6,0x3a0d3a49,
  0x3263356a,0xad972b43,0xb5dfb359,0xb8eeb7f3,0xa9b139aa,0xbbedba25,0x3340b889,0x3b983afb,0xbaa2aa16,0xb4cfbb8e,0x3c0038ad,0xb44b38e5,
  0xbb853625,0x3bbdb4c3,0xbbe432ad,0x3bfbaf8b,0xbaacb6d2,0x39243954,0xb65fbace,0x2fbd3bb8,0xb9661648,0xba603bf8,0x383a31cf,0x3b27bbb3,
  0x3219b9eb,0xbb1836f4,0xb9903be5,0x37dd3010,0xb6c6b61a,0xb80ab76f,0xb8a8b85a,0xb93cb8f3,0xbbd7bb87,0xbbf8bbfd,0xbb71bbc9,0xba4dbaf1,
  0xbbfeb9a6,0x305bb91f,0x3bcb3a97,0xb50b37d2,0xb87abbfe,0x3ba13546,0x24523a7e,0xbbb5ba54,0xb576bb63,0x340e3ba3,0xb13bbbd3,0x2c9c3bf2,
  0x386abb3d,0xba2139f8,0x3b57b835,0xbbf13432,0x39e7bc00,0xb8d6adc9,0xbacb3bde,0x372c3457,0x3bdab962,0x3764bb35,0xb9c03122,0xbaf73bef,
  0x398b39cd,0x38fd3946,0x386538b2,0x37853815,0xba85b9c9,0xbb92bb1e,0xbbfebbdd,0xbbc2bbf5,0xb66b3682,0xbb01bb94,0x387fb371,0x3a2d3beb,
  0xbac7bb76,0x3a00ad33,0x36bb3bd4,0xbbeab79b,0xbc0026ad,0x3bf32c38,0xbbd6b109,0x3ba733eb,0x3153bbff,0xb70a3b9e,0x396bba9b,0xbade390c,
  0xb5d4b5bc,0xbbb03b2c,0x32013830,0x3bf6ba67,0x3bccbb52,0x2c06b92e,0xbb83385f,0xb8c73bab,0xb9c5b982,0xba41ba04,0xbab0ba7a,0xbb10bae1,
  0xb8a3b986,0xb52fb74e,0xa94db1e8,0x33d32e91,0xbb54bb4f,0x37bdb523,0x3a9e3bc8,0xb916308d,0x3840b5c8,0x394a3bf9,0xbb42b294,0xb0a6bb0a,
  0x251bbbff,0xaf273bfc,0x327cbbe6,0xb4ab3bc0,0x3be325e4,0xbb2fb4e7,0x39e33884,0xb81aba35,0x3b73bb78,0xb46fb715,0xbbdc3ad1,0x2e2d38cc,
  0x33283676,0x3bfcba19,0x3581bab3,0xba6b3493,0x363136dd,0x34cf3581,0x32c6341a,0x2fbd3153,0xbae1bb65,0xb970ba39,0xb715b889,0xb16cb4f3,
  0xb9a12a7a,0xb924bbfe,0x3a933042,0x37dd3bcc,0x308db9aa,0x3b453b07,0xb94632ad,0xb845bbfa,0xbb68b55e,0x3b1836bb,0xbabab805,0x3a4d38a3,
  0x3bc0b625,0xbbfe2ec3,0x3b9431cf,0xba89b742,0x9cb6b95d,0xbbf8396b,0xb1b63a5c,0x3bb5b840,0x38cc9648,0x3b81bbac,0xac38b85a,0xbbce3933,
  0xbb60bb3a,0xbba1bb83,0xbbd2bbbc,0xbbf1bbe3,0x3815361a,0x39df3907,0x3b2c3a97,0x3be23b9c,0xb9afbbfd,0x3a21294d,0x388e3bee,0xbaf7b328,
  0x3beb39a6,0xb6af37a6,0xba04bbd3,0x3ac42d00,0x360ebb89,0xb7643b42,0x3855baeb,0xb8ee3a85,0x33eb3b63,0x28e8bbf5,0xb5233bde,0x389ebb21,
  0x3c00b9f0,0x2d97b9e3,0xbbdf38db,0xb44b3ac7,0xba673c00,0x358d3487,0x3bfcbab6,0x330fba15,0x3b7a3bf1,0x394a3a93,0x33893764,0xb3d39cb6,
  0x3afb3be2,0x35eb3946,0xb4c328e8,0xbaa9b8cc,0x27763af7,0xbb2fbaba,0x3a76ad97,0x30a63b60,0xaf8b3ac4,0xb994bb94,0x3bf8358d,0xb8743815,
  0xbb4c38ee,0x3bfcb1b6,0xbad5b4cf,0x381a39af,0xbbb3389e,0x3b592c38,0xb76fb970,0xb24b3beb,0xb9d2344b,0xbb923bd2,0xb0f03924,0x3a6bb60e,
  0xb8f3330f,0xbc003b2c,0xb91f3b45,0x323233eb,0xb5b1afbd,0xba00b88e,0xbbc6bb18,0xbbc2bc00,0xb7d2b16c,0xbb6fba04,0xbba3bbfe,0xb86fba67,
  0xbbffb7dd,0x370ab855,0x38b73bf8,0xbbeab631,0xbbf2b845,0x39bcb523,0x2dc93b81,0xbaa5bae1,0xb68dba4d,0xac063bdf,0x382abba1,0xbade39a1,
  0xb457ba89,0xb6543bfc,0x3b16b9df,0xbbd8308d,0x397dbbb5,0xb52fb2c6,0xbbe73a21,0xb8c73b68,0x3a49bbce,0x2311b715,0xba2536af,0xbbd93bc0,
  0xb958b785,0xbb81ba9e,0xbbefbbf3,0xba89bb73,0xbbf7bbc2,0xb9b8bb42,0xaf59b70a,0x384a3328,0xbb8bba2d,0x39dfb27c,0x34263bb0,0xbbceb98b,
  0xb4b7bbea,0x3b6c39e3,0xbafe2c06,0x3185ba85,0xaadebba7,0xb6af3bdc,0x3a58ba41,0xbbe2366b,0x3a29bade,0xbc003581,0x3a45352f,0xb2f7bac7,
  0x3b37bbf6,0x28e8b865,0xbaee37bd,0xbac43c00,0x3b13b8c7,0x3b5cbbfe,0x3463b94a,0xb8993153,0xb9f4bb10,0xb58db87f,0x3029af27,0x389e35d4,
  0x2dfbb3d3,0x399936bb,0x3bf23b2f,0x3ac13bcc,0x3552b916,0x39703bd6,0xbbbab46f,0x330fb9c5,0x3ba530a6,0xb5f7396b,0xb7c8bbfc,0x3be138a3,
  0x3bfdb4ab,0xbb45b201,0x38e038fd,0xb16cbb54,0x391b381a,0xa17fbb83,0xb8f83b92,0x3bcfb840,0x36e82e2d,0x3bfebab0,0x37febb01,0xb845251b,
  0xb77a3a6b,0x3648294d,0x3bb2ba00,0x3a8cbbe3,0xb742b93c,0x2311b340,0x37a6340e,0x3aa93966,0x3b963a4d,0x3b7f3c00,0x380f3a21,0xb0be3219,
  0x3933b50b,0x35eb3be4,0xbbf5b8d6,0x3874b6c6,0x39413bb5,0xbbffb65f,0x38d1b764,0x33ba3bd7,0x3b9c2c9c,0xb994b83a,0x34873ae8,0x324bbbfe,
  0xb7213bf1,0x3b47b990,0xbbbf2d97,0x38c1387a,0x2d00372c,0x3b59b8a8,0x3a39bbed,0xb232b576,0xbbfb3af7,0xb9743b71,0x307434cf,0x3adbb86a,
  0x3b213a0d,0x3c003bcb,0x3b073bbd,0x386f39e7,0x351738ee,0xb599a452,0xbae5b924,0xbbe9bbda,0x3a153b98,0xbb6fb13b,0x2ec3ba60,0x3aa53b3f,
  0xba09344b,0xa884bb57,0x3a643b18,0xbbc3b263,0xb4f33bfb,0x39bcbacb,0xbbac380a,0x3bd8a9b1,0xbb2aafbd,0x36a439c0,0x3402bbf8,0xba6f3aa2,
  0xbbfa3b27,0xb6543a81,0x3907b05b,0x3bd9bb85,0x2c6ab7dd,0xb9da35df,0xbbec3ba1,0xb8203aac,0x3bf53b87,0x3b6c3bec,0x392e3a7e,0x32f73721,
  0xb9e7b785,0xbbfcbb5e,0xba81bbb0,0xb43eb894,0x379b3bfe,0xbc00b80f,0x374eb835,0x38993bfb,0xbb3fba2d,0x3b329fdb,0xb3403a41,0xb8eabbd0,
  0xb90c3b3d,0x3b5cb8d1,0xbbf93122,0x3ac13517,0x29b1bba7,0xb94f3b6a,0x3be4b7bd,0xbaf4b19e,0xbbab3962,0xb9993bbf,0x34e73359,0x3be1ba09,
  0x3b85bbf6,0x353ab99d,0xb83a2f27,0xbbf03abd,0x2e91356a,0xb5f7b074,0xba19b8ad,0xbbcfbb2a,0xb966bb10,0xaba7b63c,0x38a8346f,0x3bb73a90,
  0xbb0aaa16,0xa17fbae5,0x3b1e3ace,0xba8c2c6a,0x36c6b916,0x36ff3c00,0xbbcbb8fd,0x3a50b2de,0xba35b6d2,0x36483a64,0x2d33bbe5,0xb84a3b96,
  0x3bfeb4ab,0xb9fcb602,0x313b3b01,0x37e8bbe0,0x3493b9eb,0xb9b83402,0xbb9e3bc9,0xb1853941,0x35762e2d,0x3b90b9b3,0x3acbbbf3,0x2fefb850,
  0x3a543bcf,0x2884374e,0xb9f8b648,0xbbe9bbab,0x398b3bb7,0xb4db3340,0xbbdcb9fc,0xb911bb85,0xb4323a8c,0xb6a4bbf9,0x3b3539b8,0xbbc3ae91,
  0xb66b3a50,0xad65bbe4,0x38653b90,0xbb0db966,0xbbef384a,0x39da34e7,0x2b43bb6c,0xba6f3b0a,0xbc0037e8,0x3759383a,0x387fbbfc,0xbbf636c6,
  0xb7f33185,0xbb7f3a19,0xbb8e3c00,0xb8203a35,0xb5d42fef,0xba1d38a8,0xbbd63b32,0xbba93bfe,0xb8e5b2f7,0xbbffbb1e,0xb954bb5c,0x30beb493,
  0xb9c5b43e,0xbb9fbbcb,0xb201b94f,0x3a313576,0xbbb8b899,0x3b47ad33,0xb6f43999,0xb3babbf5,0xbb54b8ea,0x3bf9313b,0xbab0353a,0x3790b9e7,
  0xb010bac1,0xb9743b9e,0x3bfdb5f7,0xb8c1b79b,0x251bbaf4,0xbb1b3acb,0x3a9e2ba7,0x2e5fbb3f,0x3af1bbe1,0x3599b92e,0xb546a17f,0xbadb390c,
  0x3b73bbf0,0x3929ba81,0x327cb6ff,0xb49f29b1,0xb825baa9,0x353aaec3,0x3b7c3994,0x3af43bfa,0x360eb0be,0x3bf43a64,0x388e3b47,0xb7372c6a,
  0x38bcb874,0x2ba73bac,0xb979bb59,0x3bf03742,0x3c0033ba,0xbb043402,0x3855b974,0xacce3b96,0x3bc5b24b,0xb6ffb907,0xb6993c00,0x3bb7b933,
  0x363138c1,0x3902bbec,0xbbdf3599,0x34ff3941,0x30d73232,0x39fcb7a6,0x3bffbb6f,0x3a50bb9c,0xb9a13adb,0xb47b380f,0x32c62884,0x3937b721,
  0x3ad8386f,0x3b903bf5,0x35a539bc,0xb7e8ad00,0x3b683be9,0x2ef538d1,0xba93b6a4,0xbb24bbfb,0x3a733aa5,0xbbfcb487,0x39d6b654,0xafef3b21,
  0x1cb63bc3,0xb7b2bbbf,0x3aba39da,0xbbfab517,0xb3a23bd8,0x3b32ba39,0xbb4a2311,0x343e3a15,0xbb603a6f,0x3a3d3074,0x31b6bb7f,0xbb9a3a09,
  0xbbe83bd9,0xb94f3b07,0xa81f35eb,0x38eab4f3,0xb9af3820,0xbbae3ae5,0xbbd23bff,0xba113b2a,0x319e389e,0xb929b426,0xbc00bb45,0xb911bb37,
  0xbbffbac1,0xb805bafe,0x382a217f,0x3bfd3b13,0xbabd330f,0x34dbba58,0x36023bfe,0xbb0db9f4,0xb68dbbe1,0x3a5c3a45,0xbbe7b648,0x3b89adfb,
  0xba90b16c,0x2d653aee,0x39b3bb81,0xbbf63552,0x397dbbcf,0xbbbc3463,0x338939b8,0x39f0bba5,0x32deb845,0xb7593029,0xbb5e39df,0xbba93bfd,
  0x3b7aba8c,0x3beebbf2,0x3a76bb6c,0x36ddb91b,0xbbe0ba89,0xba1dbbba,0x1fdbb6af,0x3a3136e8,0xa776b84a,0x3aeb37c8,0x3ad53c00,0xaa7a377a,
  0xb850bbce,0x3b9f38e0,0xbb6a28e8,0x3790b958,0x3b4cb185,0xb8db38f8,0x30f0bb5c,0x355e3bf7,0x3894bbe2,0xbbf937fe,0x399d358d,0x2e5fbb8b,
  0x39d232f7,0x341abbb2,0xbbc63999,0x395d34b7,0x3bd0bac4,0x3b1bbbef,0x363cb970,0xb49faade,0xb5b13899,0x30422f59,0x38b7b5f7,0x3b3aba29,
  0x3219b3d3,0x3b0438b7,0x3b713bfc,0x34ff397d,0x36e83aa9,0xb8b2adc9,0xbbefbb59,0xb5bcba49,0x3bd730a6,0xb902382a,0xa452bb92,0x39373b7a,
  0xb9583874,0x3371bb16,0x34263c00,0xb982bafb,0x387a381a,0x347bbbe7,0xbb573a00,0x3b242776,0xbb8b324b,0x31093a25,0x3a58bb6f,0xbb4f2f8b,
  0xb86a3a6b,0x2ef53389,0x39c0b70a,0x3bfabb4c,0xaadeb232,0xb83034c3,0xbaee39bc,0xbbff3bb3,0x3bda3bc2,0x37b23a76,0xb5df2c06,0xbb9ab9d2,
  0xbb37b86f,0xba7abbf8,0x3029b654,0x3b7838f3,0x32633bea,0xba3dbad5,0x3c00352f,0xba1135b1,0xb9f4baa5,0x3bc8376f,0xbbba2311,0x39cdb7d2,
  0xbaa23ade,0x3baeb0f0,0xb65fb94a,0xb7373bff,0x3552bbd8,0xbbe6391f,0x38e035eb,0x3682bbf2,0xbaac38c7,0xbbf43bc6,0xb9903b2f,0xacce368d,
  0x3bfdbbd9,0x3ad1bba3,0x37feb994,0x26adb457,0x38a33b9a,0xb8dba452,0xbb83bbae,0x2a7ab86a,0x37423b78,0xbab6b426,0xb907bbe6,0x39aa2ade,
  0xb8403a11,0x341abb57,0x294d3bf4,0xb55ebbda,0xb93339cd,0x3889ba58,0xb7a63ad1,0x3625bb37,0xbbe33737,0x304239c0,0x3b42bb04,0xb95db263,
  0xbb9c3682,0xb2ad3aee,0x3bf5b8b2,0x1648b9f4,0xb3282cce,0xb80535df,0xb9e33902,0xbb3a3aa2,0xad0026ad,0xb1cf3029,0xb4873371,0xb61a3552,
  0xba85b4ff,0xba5cbc00,0x3581b47b,0x3bfd3aac,0xbb21b5bc,0xb85abbba,0x3a393109,0x39a63bfd,0xbac7b937,0x3bbc365f,0xbbfeaef5,0x3b89b219,
  0xba15b982,0x3a9738e0,0xbb07b830,0x3b6336e8,0x3153bb24,0xbbee3990,0x36bb37b2,0x39f0bbd7,0x34f3bb4f,0xbbd337fe,0xaec33a7a,0x3c00b958,
  0x3bccbbfa,0x3aebbb71,0x396bba3d,0x36ddb87a,0x3bfabbff,0x3bdebbef,0x3bacbbc8,0x3b65bb8b,0x3bc03911,0x38303b6a,0xb946ad65,0xbb4fbbd0,
  0x3a353bfd,0xb85f30f0,0xbb1ebbbc,0x35c8b5b1,0x38cc3b0d,0xba7ab99d,0x3b943759,0xbbffb19e,0xb4933b89,0x31e8bbc6,0xad333bee,0xa5e4bbff,
  0xb8153bf6,0x3bc8b63c,0xac38ba1d,0xbb783abd,0xbbf539f0,0x329438b7,0x3b9ebaeb,0xb676b68d,0xbbeb3ba9,0xbbe63c00,0xbb2c3b9f,0xb9cd3a90,
  0xb79b36dd,0xb884382a,0xb92e38db,0xb9c9397d,0x33eb3a31,0xbad1b602,0xba04bbf9,0x3682b2de,0xb90c2a7a,0xbab3bbe7,0x374eb41a,0x3b763b7a,
  0xba673790,0x38b2b9b3,0xb5233b1b,0x26adbbe0,0xbbabb55e,0x3bdd3389,0xbbf9b042,0x3bff2776,0xbae12e5f,0xb3713b5e,0x3bfcb929,0xb5bcb850,
  0xae91b95d,0xbbd43a76,0x34e73805,0x3b52bb4c,0x308db49f,0xb1091fdb,0xb71534db,0xb9823894,0x3b0abb3a,0x3a9bbad5,0x3a19ba5c,0x3986b9d2,
  0x2f8bb7e8,0x3bde3979,0x376f3b32,0xb9aab0d7,0x3bb83b24,0xb1223855,0xbbfdba3d,0xaa16b9a1,0x3bb3afef,0xbab63699,0x391fb94f,0xb6253ad8,
  0x30103bfa,0xb359bbdf,0x35463bae,0xb6d2bb68,0x38f3343e,0x3889bbff,0xbba3353a,0x96483a73,0xbaf13b9a,0x38ad32c6,0x39f8bbf4,0xb9eb9cb6,
  0xb7d238ea,0xb2ad35a5,0x2dc92ba7,0x361ab3a2,0xba543a11,0xbace3a93,0xbb353b04,0xbb873b60,0x3bf23af4,0x31cf39d6,0xbb16b6ff,0xb9a6bbe8,
  0xb4323737,0xbbe5baba,0x2b43b902,0x3bfe39af,0x34573bf0,0xb85abb4a,0x3a2539fc,0xbb63b825,0xbbef2cce,0x3bc9b1b6,0xbb8e347b,0x3b3db60e,
  0xba493bb7,0x3a97a81f,0x34c3bb90,0xbc0038bc,0xb7f3b4ff,0xba7e3bd2,0x39542ef5,0x3962bc00,0xbafb3a50,0xbbd33b7c,0xbbf83bfc,0xbb653bc5,
  0x38e5b937,0x3835b88e,0x36f4b7b2,0x356ab631,0xbb13bbe9,0x31e8b6f4,0x3bf239da,0x36763af1,0x3be83911,0x340e3ab0,0xbb7cb759,0xb72cbb73,
  0x2dfbbbc3,0x32943bfd,0xb7c8bb7f,0x39c93a54,0x38253b0d,0xb8d6ba9e,0x39793a1d,0xba0db98b,0x3ba5ba6f,0xb884b546,0xb8f83bff,0x3b76b432,
  0xb8bc3bf6,0x3ae8b27c,0x3699bb9f,0xbb98366b,0x391bb820,0x3ab3b9f8,0x3bb2bb47,0x3bffbbef,0xbbc53ba9,0xbbed3bdc,0xbbff3bf9,0xbbfb3c00,
  0x377ab0be,0x3bdd3b35,0x2f593974,0xbb52b7f3,0x30d73a31,0xbbbdb865,0xb5a5bb1b,0x3b2735d4,0x3bf733ba,0xbbd42b43,0x3afeb599,0xb98638e5,
  0xbad83790,0x3a60b87f,0xb9d63929,0x393cb9c5,0x34b738c1,0x3a9bbb8e,0xba45a884,0xb5c83bb8,0xba732e5f,0xb80a3bd6,0x3b4ab4db,0x350bbb54,
  0xba293adb,0xb85f3954,0xb46336a4,0x25e43010,0x33a2b49f,0x305bb201,0x281fad65,0xac9c251b,0x3f803f80,0x3f803f80,0x3f803f80,0x3f803f80,
  0x3f803f80,0x3f803f80,0x3f803f80,0x3f803f80,0x3f803f80,0x3f803f80,0x3f803f80,0x3f803f80,0x3f803f80,0x3f803f80,0x3f803f80,0x3f803f80,
  0x3f803f80,0x3f803f80,0x3f803f80,0x3f803f80,0x3f803f80,0x3f803f80,0x3f803f80,0x3f803f80,0x3f803f80,0x3f803f80,0x3f803f80,0x3f803f80,
  0x3f803f80,0x3f803f80,0x3f803f80,0x3f803f80,0x3f803f80,0x3f803f80,0x3f803f80,0x3f803f80,0x3f803f80,0x3f803f80,0x3f803f80,0x3f803f80,
  0x3f803f80,0x3f803f80,0x3f803f80,0x3f803f80,0x3f803f80,0x3f803f80,0x3f803f80,0x3f803f80,0x3f803f80,0x3f803f80,0x3f803f80,0x3f803f80,
  0x3f803f80,0x3f803f80,0x3f803f80,0x3f803f80,0x3f803f80,0x3f803f80,0x3f803f80,0x3f803f80,0x3f803f80,0x3f803f80,0x3f803f80,0x3f803f80,
  0x3f803f80,0x3f803f80,0x3f803f80,0x3f803f80,0x3f803f80,0x3f803f80,0x3f803f80,0x3f803f80,0x3f803f80,0x3f803f80,0x3f803f80,0x3f803f80,
  0x3f803f80,0x3f803f80,0x3f803f80,0x3f803f80,0x3f803f80,0x3f803f80,0x3f803f80,0x3f803f80,0x3f803f80,0x3f803f80,0x3f803f80,0x3f803f80,
  0x3f803f80,0x3f803f80,0x3f803f80,0x3f803f80,0x3f803f80,0x3f803f80,0x3f803f80,0x3f803f80,0x3f803f80,0x3f803f80,0x3f803f80,0x3f803f80,
  0x3f803f80,0x3f803f80,0x3f803f80,0x3f803f80,0x3f803f80,0x3f803f80,0x3f803f80,0x3f803f80,0x3f803f80,0x3f803f80,0x3f803f80,0x3f803f80,
  0x3f803f80,0x3f803f80,0x3f803f80,0x3f803f80,0x3f803f80,0x3f803f80,0x3f803f80,0x3f803f80,0x3f803f80,0x3f803f80,0x3f803f80,0x3f803f80,
  0x3f803f80,0x3f803f80,0x3f803f80,0x3f803f80,0x3f803f80,0x3f803f80,0x3f803f80,0x3f803f80,0x3f803f80,0x3f803f80,0x3f803f80,0x3f803f80,
  0x3f803f80,0x3f803f80,0x3f803f80,0x3f803f80,0x3f803f80,0x3f803f80,0x3f803f80,0x3f803f80,0x3f803f80,0x3f803f80,0x3f803f80,0x3f803f80,
  0x3f803f80,0x3f803f80,0x3f803f80,0x3f803f80,0x3f803f80,0x3f803f80,0x3f803f80,0x3f803f80,0x3f803f80,0x3f803f80,0x3f803f80,0x3f803f80,
  0x3f803f80,0x3f803f80,0x3f803f80,0x3f803f80,0x3f803f80,0x3f803f80,0x3f803f80,0x3f803f80,0x3f803f80,0x3f803f80,0x3f803f80,0x3f803f80,
  0x3f803f80,0x3f803f80,0x3f803f80,0x3f803f80,0x3f803f80,0x3f803f80,0x3f803f80,0x3f803f80,0x3f803f80,0x3f803f80,0x3f803f80,0x3f803f80,
  0x3f803f80,0x3f803f80,0x3f803f80,0x3f803f80,0x3f803f80,0x3f803f80,0x3f803f80,0x3f803f80,0x3f803f80,0x3f803f80,0x3f803f80,0x3f803f80,
  0x3f803f80,0x3f803f80,0x3f803f80,0x3f803f80,0x3f803f80,0x3f803f80,0x3f803f80,0x3f803f80,0x3f803f80,0x3f803f80,0x3f803f80,0x3f803f80,
  0x3f803f80,0x3f803f80,0x3f803f80,0x3f803f80,0x3f803f80,0x3f803f80,0x3f803f80,0x3f803f80,0x3f803f80,0x3f803f80,0x3f803f80,0x3f803f80,
  0x3f803f80,0x3f803f80,0x3f803f80,0x3f803f80,0x3f803f80,0x3f803f80,0x3f803f80,0x3f803f80,0x3f803f80,0x3f803f80,0x3f803f80,0x3f803f80,
  0x3f803f80,0x3f803f80,0x3f803f80,0x3f803f80,0x3f803f80,0x3f803f80,0x3f803f80,0x3f803f80,0x3f803f80,0x3f803f80,0x3f803f80,0x3f803f80,
  0x3f803f80,0x3f803f80,0x3f803f80,0x3f803f80,0x3f803f80,0x3f803f80,0x3f803f80,0x3f803f80,0x3f803f80,0x3f803f80,0x3f803f80,0x3f803f80,
  0x3f803f80,0x3f803f80,0x3f803f80,0x3f803f80,0x3f803f80,0x3f803f80,0x3f803f80,0x3f803f80,0x3f803f80,0x3f803f80,0x3f803f80,0x3f803f80,
  0x3f803f80,0x3f803f80,0x3f803f80,0x3f803f80,0x3f803f80,0x3f803f80,0x3f803f80,0x3f803f80,0x3f803f80,0x3f803f80,0x3f803f80,0x3f803f80,
  0x3f803f80,0x3f803f80,0x3f803f80,0x3f803f80,0x3f803f80,0x3f803f80,0x3f803f80,0x3f803f80,0x3f803f80,0x3f803f80,0x3f803f80,0x3f803f80,
  0x3f803f80,0x3f803f80,0x3f803f80,0x3f803f80,0x3f803f80,0x3f803f80,0x3f803f80,0x3f803f80,0x3f803f80,0x3f803f80,0x3f803f80,0x3f803f80,
  0x3f803f80,0x3f803f80,0x3f803f80,0x3f803f80,0x3f803f80,0x3f803f80,0x3f803f80,0x3f803f80,0x3f803f80,0x3f803f80,0x3f803f80,0x3f803f80,
  0x3f803f80,0x3f803f80,0x3f803f80,0x3f803f80,0x3f803f80,0x3f803f80,0x3f803f80,0x3f803f80,0x3f803f80,0x3f803f80,0x3f803f80,0x3f803f80,
  0x3f803f80,0x3f803f80,0x3f803f80,0x3f803f80,0x3f803f80,0x3f803f80,0x3f803f80,0x3f803f80,0x3f803f80,0x3f803f80,0x3f803f80,0x3f803f80,
  0x3f803f80,0x3f803f80,0x3f803f80,0x3f803f80,0x3f803f80,0x3f803f80,0x3f803f80,0x3f803f80,0x3f803f80,0x3f803f80,0x3f803f80,0x3f803f80,
  0x3f803f80,0x3f803f80,0x3f803f80,0x3f803f80,0x3f803f80,0x3f803f80,0x3f803f80,0x3f803f80,0x3f803f80,0x3f803f80,0x3f803f80,0x3f803f80,
  0x3f803f80,0x3f803f80,0x3f803f80,0x3f803f80,0x3f803f80,0x3f803f80,0x3f803f80,0x3f803f80,0x3f803f80,0x3f803f80,0x3f803f80,0x3f803f80,
  0x3f803f80,0x3f803f80,0x3f803f80,0x3f803f80,0x3f803f80,0x3f803f80,0x3f803f80,0x3f803f80,0x3f803f80,0x3f803f80,0x3f803f80,0x3f803f80,
  0x3f803f80,0x3f803f80,0x3f803f80,0x3f803f80,0x3f803f80,0x3f803f80,0x3f803f80,0x3f803f80,0x3f803f80,0x3f803f80,0x3f803f80,0x3f803f80,
  0x3f803f80,0x3f803f80,0x3f803f80,0x3f803f80,0x3f803f80,0x3f803f80,0x3f803f80,0x3f803f80,0x3f803f80,0x3f803f80,0x3f803f80,0x3f803f80,
  0x3f803f80,0x3f803f80,0x3f803f80,0x3f803f80,0x3f803f80,0x3f803f80,0x3f803f80,0x3f803f80,0x3f803f80,0x3f803f80,0x3f803f80,0x3f803f80,
  0x3f803f80,0x3f803f80,0x3f803f80,0x3f803f80,0x3f803f80,0x3f803f80,0x3f803f80,0x3f803f80,0x3f803f80,0x3f803f80,0x3f803f80,0x3f803f80,
  0x3f803f80,0x3f803f80,0x3f803f80,0x3f803f80,0x3f803f80,0x3f803f80,0x3f803f80,0x3f803f80,0x3f803f80,0x3f803f80,0x3f803f80,0x3f803f80,
  0x3f803f80,0x3f803f80,0x3f803f80,0x3f803f80,0x3f803f80,0x3f803f80,0x3f803f80,0x3f803f80,0x3f803f80,0x3f803f80,0x3f803f80,0x3f803f80,
  0x3f803f80,0x3f803f80,0x3f803f80,0x3f803f80,0x3f803f80,0x3f803f80,0x3f803f80,0x3f803f80,0x3f803f80,0x3f803f80,0x3f803f80,0x3f803f80,
  0x3f803f80,0x3f803f80,0x3f803f80,0x3f803f80,0x3f803f80,0x3f803f80,0x3f803f80,0x3f803f80,0x3f803f80,0x3f803f80,0x3f803f80,0x3f803f80,
  0x3f803f80,0x3f803f80,0x3f803f80,0x3f803f80,0x3f803f80,0x3f803f80,0x3f803f80,0x3f803f80,0x3f803f80,0x3f803f80,0x3f803f80,0x3f803f80,
  0x3f803f80,0x3f803f80,0x3f803f80,0x3f803f80,0x3f803f80,0x3f803f80,0x3f803f80,0x3f803f80,0x3f803f80,0x3f803f80,0x3f803f80,0x3f803f80,
  0x3f803f80,0x3f803f80,0x3f803f80,0x3f803f80,
};

__device__ __align__(128) float    g_part[16][8][2176];
__device__ __align__(128) float    g_kv[16][2176];
__device__ __align__(128) uint4    g_o[16 * 16 * 1024];
__device__ __align__(128) unsigned g_ocnt[2 * 16 * 32];
__device__ unsigned g_epoch[128];
#define GSTAMP(role, i) do {} while (0)
#define STAMP(role, i) do {} while (0)
#define PDUMP(role) do {} while (0)
#define PROF_SMEM 0

constexpr int STAGE_BYTES = 57344;
constexpr int OFF_H = 4 * 16384, OFF_VP = 9 * 16384, OFF_SPARE = 10 * 16384;
constexpr int OFF_XT = 172032, XT_STRIDE = 4112;
constexpr int OFF_BAR = 204928, OFF_EPOCH = OFF_BAR + 640, OFF_EX = OFF_BAR + 656, OFF_D = OFF_BAR + 672, OFF_SCALE = OFF_BAR + 704;
constexpr int OFF_F2F = 205824, OFF_F2I = 207872, OFF_F4 = 209920, OFF_ONES = 214016, OFF_KVB = 214016;
constexpr int OFF_STG = 219136, STG_STRIDE = 4352, SMEM_TOTAL = 232192 + PROF_SMEM;
enum { B_FULL1 = 0, B_EMPTY1 = 3, B_Q = 6, B_ODONE1 = 7, B_O1RDY = 8, B_H = 9, B_XRAW = 10, B_XT = 11, B_KV = 12, B_Y = 13,  B_AFREE = 15,
       B_STG = 18, B_ODONE = 24, B_XFREE = 25, B_FULL2 = 33, B_CONS2 = 49, B_SFREE = 14, B_KV1 = 61, B_PKRDY = 62, B_PKFREE = 64, B_H2 = 65, B_G1DONE = 66, B_COUNT = 67, B_FIRST = 67 };
constexpr uint64_t SLOT_A = 0x6859468594685948ull, SLOT_B = 0x7103271032710326ull;
constexpr int NPRE = 6, BEARLY = 3;
__host__ __device__ constexpr int bar_count(int i) {
  return i < B_EMPTY1 ? 1 : i < B_Q ? 4 : i == B_XT ? 4 : i == B_H ? 4 : (i == B_SFREE || i == B_G1DONE) ? 2 : i >= B_PKFREE ? 4 : i >= B_PKRDY ? 8 : i == B_Y ? 9
       : (i >= B_AFREE && i < B_STG) ? 16 : (i == B_ODONE || i == B_ODONE1) ? 8 : (i >= B_XFREE && i < B_FULL2) ? 4
       : i == B_KV1 ? 1 : i >= B_CONS2 ? 4 : (i >= B_FULL2 && i < B_FULL2 + NPRE) ? 2 : 1;
}
__host__ __device__ constexpr uint64_t bar_counts(int r) {
  uint64_t v = 0;
  for (int w = 0; w < 11; w++) v |= (uint64_t)(bar_count(1 + 11 * r + w) - 1) << (4 * w);
  return v;
}
constexpr uint32_t SW128 = 64 | (1u << 30);
constexpr int SPIN_LIMIT = 1 << 22;
#define SPLIT0 2
#define PFD 3
#define PD1 700
#define PD2 450
#define QPF 6
#define BPACE 250
#define OCH 3
#define O1D 1
#define HOLD2 12
#define D1 100
#define TRICK 3
#define HSTART 1500
#define PACE 800

__device__ __forceinline__ uint32_t smem_u32(const void* p) { return (uint32_t)__cvta_generic_to_shared(p); }
__device__ __forceinline__ void wg_fence() { asm volatile("wgmma.fence.sync.aligned;" ::: "memory"); }
__device__ __forceinline__ void wg_commit() { asm volatile("wgmma.commit_group.sync.aligned;" ::: "memory"); }
template <int N> __device__ __forceinline__ void wg_wait() { asm volatile("wgmma.wait_group.sync.aligned %0;" ::"n"(N) : "memory"); }
template <int N> __device__ __forceinline__ void keep(float (&d)[N]) {
#pragma unroll
  for (int i = 0; i < N; i++) asm volatile("" : "+f"(d[i])::"memory");
}
__device__ __forceinline__ void mbar_init(uint32_t bar, int cnt) { asm volatile("mbarrier.init.shared::cta.b64 [%0], %1;" ::"r"(bar), "r"(cnt)); }
__device__ __forceinline__ void mbar_expect(uint32_t bar, int bytes) { asm volatile("mbarrier.arrive.expect_tx.shared::cta.b64 _, [%0], %1;" ::"r"(bar), "r"(bytes) : "memory"); }
__device__ __forceinline__ void mbar_arrive(uint32_t bar) { asm volatile("mbarrier.arrive.shared::cta.b64 _, [%0];" ::"r"(bar) : "memory"); }
__device__ __forceinline__ void mbar_arrive_cl(uint32_t bar, uint32_t cta) {
  asm volatile("{\n.reg .b32 r;\nmapa.shared::cluster.u32 r, %0, %1;\nmbarrier.arrive.shared::cluster.b64 _, [r];\n}\n" ::"r"(bar), "r"(cta) : "memory");
}
__device__ __forceinline__ void mbar_wait(uint32_t bar, uint32_t parity) {
  asm volatile("{\n.reg .pred p;\n.reg .u32 n;\nmov.u32 n, 0;\n"
               "W_%=:\nmbarrier.try_wait.parity.shared::cta.b64 p, [%0], %1;\n@p bra D_%=;\n"
               "add.u32 n, n, 1;\nsetp.lt.u32 p, n, %2;\n@p bra W_%=;\ntrap;\nD_%=:\n}\n" ::"r"(bar), "r"(parity), "n"(SPIN_LIMIT) : "memory");
}
__device__ __forceinline__ void fence_async() { asm volatile("fence.proxy.async.shared::cta;" ::: "memory"); }
__device__ __forceinline__ void bar_sync(int id) { asm volatile("bar.sync %0, 128;" ::"r"(id) : "memory"); }
__device__ __forceinline__ void tma2d(uint32_t dst, const CUtensorMap* m, int c0, int c1, uint32_t bar) {
  asm volatile("cp.async.bulk.tensor.2d.shared::cluster.global.mbarrier::complete_tx::bytes [%0], [%1, {%3, %4}], [%2];"
               ::"r"(dst), "l"(m), "r"(bar), "r"(c0), "r"(c1) : "memory");
}
__device__ __forceinline__ void tma2d_mc(uint32_t dst, const CUtensorMap* m, int c0, int c1, uint32_t bar) {
  asm volatile("cp.async.bulk.tensor.2d.shared::cluster.global.mbarrier::complete_tx::bytes.multicast::cluster [%0], [%1, {%3, %4}], [%2], %5;"
               ::"r"(dst), "l"(m), "r"(bar), "r"(c0), "r"(c1), "h"((uint16_t)3) : "memory");
}
__device__ __forceinline__ void tma3d(uint32_t dst, const CUtensorMap* m, int c0, int c1, int c2, uint32_t bar) {
  asm volatile("cp.async.bulk.tensor.3d.shared::cluster.global.mbarrier::complete_tx::bytes [%0], [%1, {%3, %4, %5}], [%2];"
               ::"r"(dst), "l"(m), "r"(bar), "r"(c0), "r"(c1), "r"(c2) : "memory");
}
__device__ __forceinline__ void tma4d(uint32_t dst, const CUtensorMap* m, int c0, int c1, int c2, int c3, uint32_t bar) {
  asm volatile("cp.async.bulk.tensor.4d.shared::cluster.global.mbarrier::complete_tx::bytes [%0], [%1, {%3, %4, %5, %6}], [%2];"
               ::"r"(dst), "l"(m), "r"(bar), "r"(c0), "r"(c1), "r"(c2), "r"(c3) : "memory");
}
__device__ __forceinline__ void bulk_ld(uint32_t dst, const void* src, int bytes, uint32_t bar) {
  asm volatile("cp.async.bulk.shared::cluster.global.mbarrier::complete_tx::bytes [%0], [%1], %2, [%3];" ::"r"(dst), "l"(src), "r"(bytes), "r"(bar) : "memory");
}
__device__ __forceinline__ void bulk_ld_mc(uint32_t dst, const void* src, int bytes, uint32_t bar) {
  asm volatile("cp.async.bulk.shared::cluster.global.mbarrier::complete_tx::bytes.multicast::cluster [%0], [%1], %2, [%3], %4;"
               ::"r"(dst), "l"(src), "r"(bytes), "r"(bar), "h"((uint16_t)3) : "memory");
}
__device__ __forceinline__ void tma2d_st(const CUtensorMap* m, uint32_t src, int c0, int c1) {
  asm volatile("cp.async.bulk.tensor.2d.global.shared::cta.bulk_group [%0, {%2, %3}], [%1];" ::"l"(m), "r"(src), "r"(c0), "r"(c1) : "memory");
}
__device__ __forceinline__ void ldsm4(uint32_t (&r)[4], uint32_t a) {
  asm volatile("ldmatrix.sync.aligned.m8n8.x4.shared.b16 {%0,%1,%2,%3}, [%4];" : "=r"(r[0]), "=r"(r[1]), "=r"(r[2]), "=r"(r[3]) : "r"(a) : "memory");
}
__device__ __forceinline__ void ldsm4t(uint32_t (&r)[4], uint32_t a) {
  asm volatile("ldmatrix.sync.aligned.m8n8.x4.trans.shared.b16 {%0,%1,%2,%3}, [%4];" : "=r"(r[0]), "=r"(r[1]), "=r"(r[2]), "=r"(r[3]) : "r"(a) : "memory");
}
__device__ __forceinline__ void stsm4(uint32_t a, uint32_t r0, uint32_t r1, uint32_t r2, uint32_t r3) {
  asm volatile("stmatrix.sync.aligned.m8n8.x4.shared.b16 [%0], {%1,%2,%3,%4};" ::"r"(a), "r"(r0), "r"(r1), "r"(r2), "r"(r3) : "memory");
}
__device__ __forceinline__ uint32_t pk2(float lo, float hi) { uint32_t r; asm("cvt.rn.bf16x2.f32 %0, %1, %2;" : "=r"(r) : "f"(hi), "f"(lo)); return r; }
__device__ __forceinline__ uint32_t hmul(uint32_t a, uint32_t b) { uint32_t r; asm("mul.rn.bf16x2 %0, %1, %2;" : "=r"(r) : "r"(a), "r"(b)); return r; }
__device__ __forceinline__ uint32_t hadd(uint32_t a, uint32_t b) { uint32_t r; asm("add.rn.bf16x2 %0, %1, %2;" : "=r"(r) : "r"(a), "r"(b)); return r; }
__device__ __forceinline__ uint32_t hmin(uint32_t a, uint32_t b) { uint32_t r; asm("min.bf16x2 %0, %1, %2;" : "=r"(r) : "r"(a), "r"(b)); return r; }
__device__ __forceinline__ uint32_t hmaxabs(uint32_t a, uint32_t b) { uint32_t r; asm("max.xorsign.abs.bf16x2 %0, %1, %2;" : "=r"(r) : "r"(a), "r"(b)); return r; }
__device__ __forceinline__ float ex2(float x) { float r; asm("ex2.approx.ftz.f32 %0, %1;" : "=f"(r) : "f"(x)); return r; }
__device__ __forceinline__ float rcp_fast(float x) { float r; asm("rcp.approx.ftz.f32 %0, %1;" : "=f"(r) : "f"(x)); return r; }
__device__ __forceinline__ uint32_t phi2(float lo, float hi) {
  uint32_t t;
  asm("cvt.rn.relu.bf16x2.f32 %0, %1, %2;" : "=r"(t) : "f"(hi), "f"(lo));
  const uint32_t e = pk2(ex2(lo * 1.4426950408889634f), ex2(hi * 1.4426950408889634f));
  return hadd(hadd(t, hmin(e, 0x3F803F80u)), 0x35863586u);
}
__device__ __forceinline__ bool opaque_true() { uint32_t v; asm volatile("mov.u32 %0, %%nctaid.y;" : "=r"(v)); return v != 0; }
__device__ __forceinline__ int norm_exp(uint32_t (&v)[32], float f0) {
  uint32_t m[4] = {hmaxabs(__float_as_uint(f0) >> 16, v[0]), v[1], v[2], v[3]};
#pragma unroll
  for (int i = 4; i < 32; i++) m[i & 3] = hmaxabs(m[i & 3], v[i]);
  m[0] = hmaxabs(hmaxabs(m[0], m[1]), hmaxabs(m[2], m[3]));
  const int e = min(max((int)(__reduce_max_sync(~0u, max(m[0] & 0x7FFFu, (m[0] >> 16) & 0x7FFFu)) >> 7), 1), 253);
  if (e > 141) {
#pragma unroll
    for (int i = 0; i < 32; i++) v[i] = hmul(v[i], 0x07000700u);
  }
  return e;
}
__device__ __forceinline__ void norm_cvt(uint32_t (&v)[32], float f0, int e) {
  const uint32_t sc = (e > 141 ? 255 - e : 142 - e) * 0x00800080u;
#pragma unroll
  for (int i = 0; i < 32; i++) {
    const uint32_t a = hmul(v[i], sc);
    v[i] = (a & 0x0FFF0FFFu) * 7 + a;
  }
  v[0] = __byte_perm(v[0], __half_as_ushort(__float2half_rn(f0 * __uint_as_float((254 - e) << 23))), 0x3254);
}
__device__ __forceinline__ void poll_ge(const unsigned* p, unsigned target) {
#pragma unroll 1
  for (int n = 0; n < SPIN_LIMIT; n++) {
    unsigned v;
    asm volatile("ld.relaxed.gpu.global.u32 %0, [%1];" : "=r"(v) : "l"(p) : "memory");
    if (__all_sync(~0u, (int)(v - target) >= 0)) { asm volatile("fence.acquire.gpu;" ::: "memory"); return; }
  }
  __trap();
}

__device__ __forceinline__ bool elect_one() {
  uint32_t p;
  asm volatile("{\n.reg .pred p;\nelect.sync _|p, 0xffffffff;\nselp.u32 %0, 1, 0, p;\n}\n" : "=r"(p));
  return p;
}
__device__ __forceinline__ uint4 ld_na4(const void* p) {
  uint4 v;
  asm volatile("ld.global.L1::no_allocate.v4.u32 {%0,%1,%2,%3}, [%4];" : "=r"(v.x), "=r"(v.y), "=r"(v.z), "=r"(v.w) : "l"(p) : "memory");
  return v;
}
__device__ __forceinline__ void st_cg4(void* p, uint4 v) {
  asm volatile("st.global.cg.v4.u32 [%0], {%1,%2,%3,%4};" ::"l"(p), "r"(v.x), "r"(v.y), "r"(v.z), "r"(v.w) : "memory");
}
__device__ __forceinline__ uint32_t mapa(uint32_t a, uint32_t cta) { uint32_t r; asm("mapa.shared::cluster.u32 %0, %1, %2;" : "=r"(r) : "r"(a), "r"(cta)); return r; }
__device__ __forceinline__ void st_async(uint32_t a, uint32_t v, uint32_t bar) {
  asm volatile("st.async.weak.shared::cluster.mbarrier::complete_tx::bytes.b32 [%0], %1, [%2];" ::"r"(a), "r"(v), "r"(bar) : "memory");
}
__device__ __forceinline__ void st_async4(uint32_t a, uint32_t x, uint32_t y, uint32_t z, uint32_t w, uint32_t bar) {
  asm volatile("st.async.weak.shared::cluster.mbarrier::complete_tx::bytes.v4.b32 [%0], {%1,%2,%3,%4}, [%5];" ::"r"(a), "r"(x), "r"(y), "r"(z), "r"(w), "r"(bar) : "memory");
}
__device__ __forceinline__ void tma3d_st(const CUtensorMap* m, uint32_t src, int c0, int c1, int c2) {
  asm volatile("cp.async.bulk.tensor.3d.global.shared::cta.bulk_group [%0, {%2, %3, %4}], [%1];" ::"l"(m), "r"(src), "r"(c0), "r"(c1), "r"(c2) : "memory");
}
__device__ __forceinline__ uint4 ld_rlx4(const void* p) {
  uint4 v;
  asm volatile("{\n.reg .b128 t;\n.reg .b64 a, b;\nld.relaxed.gpu.global.b128 t, [%4];\nmov.b128 {a, b}, t;\nmov.b64 {%0, %1}, a;\nmov.b64 {%2, %3}, b;\n}\n"
               : "=r"(v.x), "=r"(v.y), "=r"(v.z), "=r"(v.w) : "l"(p) : "memory");
  return v;
}
__device__ __forceinline__ void ld_stale4(uint4& v, const void* p, uint32_t tag) {
  asm volatile("{\n.reg .b128 t;\n.reg .b64 a, b;\n.reg .b32 x;\n.reg .pred p;\n"
               "lop3.b32 x, %0, %5, 1, 0x28;\nsetp.ne.u32 p, x, 0;\n"
               "mov.b64 a, {%0, %1};\nmov.b64 b, {%2, %3};\nmov.b128 t, {a, b};\n"
               "@p ld.relaxed.gpu.global.b128 t, [%4];\n"
               "mov.b128 {a, b}, t;\nmov.b64 {%0, %1}, a;\nmov.b64 {%2, %3}, b;\n}\n"
               : "+r"(v.x), "+r"(v.y), "+r"(v.z), "+r"(v.w) : "l"(p), "r"(tag) : "memory");
}
__device__ __forceinline__ void st_tag4(void* p, float a, float b, float c, float d, uint32_t tag) {
  asm volatile("{\n.reg .b128 t;\n.reg .b64 a, b;\nmov.b64 a, {%1, %2};\nmov.b64 b, {%3, %4};\nmov.b128 t, {a, b};\nst.relaxed.gpu.global.b128 [%0], t;\n}\n"
               ::"l"(p), "r"((__float_as_uint(a) & ~1u) | tag), "f"(b), "f"(c), "f"(d) : "memory");
}
__device__ __forceinline__ uint32_t stale8(const uint4 (&f)[8], uint32_t tag) {
  uint32_t r[4];
#pragma unroll
  for (int i = 0; i < 4; i++) asm("lop3.b32 %0, %1, %2, %3, 0x7E;" : "=r"(r[i]) : "r"(f[2 * i].x), "r"(f[2 * i + 1].x), "r"(tag));
  asm("lop3.b32 %0, %0, %1, %2, 0xFE;" : "+r"(r[0]) : "r"(r[1]), "r"(r[2]));
  return r[0] | r[3];
}

struct ConvC { uint32_t a1[2][4], wa[2], wb[2], sg; };
__device__ __forceinline__ uint64_t dsc(uint32_t lo, uint32_t hi) { return ((uint64_t)hi << 32) | lo; }
__device__ __forceinline__ uint32_t hfma(uint32_t a, uint32_t b, uint32_t c) { uint32_t r; asm("fma.rn.f16x2 %0, %1, %2, %3;" : "=r"(r) : "r"(a), "r"(b), "r"(c)); return r; }
__device__ __forceinline__ uint32_t hfnma(uint32_t a, uint32_t b, uint32_t c) { uint32_t r; asm("{.reg .b32 n; neg.f16x2 n, %1; fma.rn.f16x2 %0, n, %2, %3;}" : "=r"(r) : "r"(a), "r"(b), "r"(c)); return r; }
__device__ __forceinline__ uint32_t hmul16(uint32_t a, uint32_t b) { uint32_t r; asm("mul.rn.f16x2 %0, %1, %2;" : "=r"(r) : "r"(a), "r"(b)); return r; }
template <int N> __device__ __forceinline__ void keepu(uint32_t (&d)[N]) {
#pragma unroll
  for (int i = 0; i < N; i++) asm volatile("" : "+r"(d[i])::"memory");
}
__device__ __forceinline__ void conv_m1(const ConvC& K, uint32_t (&u)[16], uint32_t l) {
  wg_fence();
  wgmma_hrs_n64<1>(u, K.a1[0][0], K.a1[0][1], K.a1[0][2], K.a1[0][3], dsc(l, 32), 0);
  wgmma_hrs_n64<1>(u, K.a1[1][0], K.a1[1][1], K.a1[1][2], K.a1[1][3], dsc(l + 16, 32), 1);
  wg_commit();
}
__device__ __forceinline__ void conv_s2(const ConvC& K, uint32_t (&u)[16], uint32_t (&Z)[2][8], uint32_t dfl) {
  uint32_t fr[8], fi[8];
#pragma unroll
  for (int c = 0; c < 8; c++) {
    const uint32_t r = hfma(K.wa[c & 1], u[2 * c + 1], u[2 * c]);
    fi[c] = hfma(K.wb[c & 1], r, u[2 * c + 1]);
    fr[c] = hfma(K.wa[c & 1], fi[c], r);
  }
  wg_fence();
#pragma unroll
  for (int p = 0; p < 2; p++) {
    wgmma_hrs_n32<0>(Z[p], fr[4 * p], fr[4 * p + 2], fr[4 * p + 1], fr[4 * p + 3], dsc(dfl, 32), 0);
    wgmma_hrs_n32<0>(Z[p], fi[4 * p], fi[4 * p + 2], fi[4 * p + 1], fi[4 * p + 3], dsc(dfl + 16, 32), 1);
  }
  wg_commit();
}
__device__ __forceinline__ void conv_win(const ConvC& K, const uint32_t (&X)[2][8], uint32_t (&W)[2][8]) {
#pragma unroll
  for (int b = 0; b < 4; b++)
#pragma unroll
    for (int c = 0; c < 2; c++) {
      const uint32_t xr = X[b >> 1][2 * c + (b & 1)], xi = X[b >> 1][4 + 2 * c + (b & 1)];
      const int a = b ? b - 1 : 0;
      W[b >> 1][2 * c + (b & 1)] = b ? hfnma(K.sg, X[a >> 1][4 + 2 * c + (a & 1)], xr) : hmul16(xr, 0x3C003C00u);
      W[b >> 1][4 + 2 * c + (b & 1)] = b ? hfma(K.sg, X[a >> 1][2 * c + (a & 1)], xi) : hmul16(xi, 0x3C003C00u);
    }
}
template <int p>
__device__ __forceinline__ void conv_pw(uint32_t (&X)[2][8], uint32_t (&H)[2][8], uint32_t (&V)[8], uint32_t dil) {
  uint32_t pr[2][2], pi[2][2];
#pragma unroll
  for (int jj = 0; jj < 2; jj++)
#pragma unroll
    for (int c = 0; c < 2; c++) {
      const int j = 2 * p + jj;
      uint32_t sr = 0, si = 0;
#pragma unroll
      for (int a = 0; a <= j; a++) {
        const int b = j - a;
        const uint32_t hr = H[a >> 1][2 * c + (a & 1)], hi = H[a >> 1][4 + 2 * c + (a & 1)];
        const uint32_t xr = X[b >> 1][2 * c + (b & 1)], xi = X[b >> 1][4 + 2 * c + (b & 1)];
        sr = a == 0 ? hmul16(hr, xr) : hfma(hr, xr, sr);
        si = a == 0 ? hmul16(hr, xi) : hfma(hr, xi, si);
        sr = hfnma(hi, xi, sr);
        si = hfma(hi, xr, si);
      }
      pr[jj][c] = sr; pi[jj][c] = si;
    }
  wg_fence();
  wgmma_hrs_n32<0>(V, pr[0][0], pr[1][0], pr[0][1], pr[1][1], dsc(dil, 32), 0);
  wgmma_hrs_n32<0>(V, pi[0][0], pi[1][0], pi[0][1], pi[1][1], dsc(dil + 16, 32), 1);
  wg_commit();
}
template <int p>
__device__ __forceinline__ void conv_it(const ConvC& K, uint32_t (&V)[8], uint32_t vst) {
#pragma unroll
  for (int jj = 0; jj < 2; jj++) {
    uint32_t wr[2], wi[2];
#pragma unroll
    for (int c = 0; c < 2; c++) {
      const uint32_t r = hfnma(K.wa[c], V[4 + 2 * c + jj], V[2 * c + jj]);
      wi[c] = hfnma(K.wb[c], r, V[4 + 2 * c + jj]);
      wr[c] = hfnma(K.wa[c], wi[c], r);
    }
    stsm4(vst + (2 * p + jj) * 2048, wr[0], wr[1], wi[0], wi[1]);
  }
}
__device__ __forceinline__ void conv_m4(uint32_t (&y)[8], uint32_t (&a)[4][4], uint32_t d4l) {
  wg_fence();
  wgmma_hrs_n32<0>(y, a[0][0], a[0][1], a[0][2], a[0][3], dsc(d4l, 64), 0);
#pragma unroll
  for (int s = 1; s < 4; s++) wgmma_hrs_n32<0>(y, a[s][0], a[s][1], a[s][2], a[s][3], dsc(d4l + s * 16, 64), 1);
  wg_commit();
}

struct Params {
  CUtensorMap tmX0, tmW, tmX, tmWo, tmWo1, tmK, tmV, tmQ, tmOA, tmOB;
  const __nv_bfloat16 *shift_k, *h, *D, *x, *w, *wo, *q;
  float *part, *kv;
  uint4* o;
  unsigned *ocnt, *epoch;
  const uint32_t *thr, *img;
};

__global__ void __cluster_dims__(2, 1, 1) __launch_bounds__(384, 1) fused_kernel(const __grid_constant__ Params P) {
  extern __shared__ __align__(1024) uint8_t smem[];
  const uint32_t sb = __shfl_sync(~0u, smem_u32(smem), 0);
  const uint32_t bars = sb + OFF_BAR;
  const int tid = threadIdx.x, lane = tid & 31;
  const int warp = __shfl_sync(~0u, tid >> 5, 0);
  const int rank = blockIdx.x & 1, cl = blockIdx.x >> 1;
  const unsigned c7 = cl + 6, g7 = (c7 * 37) >> 8;
  const int mb = cl < 4 ? 4 + cl : cl < 36 ? (cl - 4) >> 3 : g7 - 2;
  const int hq = cl < 4 ? 0 : cl < 36 ? (cl - 4) & 7 : 1 + c7 - 7 * g7;
  const int hp = 2 * hq + rank;
  const int rb = 2 * mb + (hq >> 2), cb = hq & 3;
#define BAR(i) (bars + 8 * (i))

  if (tid == 0) { STAMP(0, 0); GSTAMP(0, 30); }
  if (warp == 8) {
    if (elect_one()) {
      mbar_init(BAR(B_FULL1), 1);
      mbar_init(BAR(B_FIRST), 1);
      asm volatile("fence.mbarrier_init.release.cluster;" ::: "memory");
      mbar_expect(BAR(B_FIRST), STAGE_BYTES - 16384);
      tma2d(sb, &P.tmX0, 0, mb * 256, BAR(B_FIRST));
      tma2d(sb + 16384, &P.tmX0, 0, mb * 256 + 128, BAR(B_FIRST));
      tma3d(sb + 32768, &P.tmW, hp * 64, 0, 0, BAR(B_FIRST));
    }
    if (lane == 0) STAMP(3, 21);
  } else if (lane == 0) {
    const int wi = warp - (warp > 8);
#pragma unroll
    for (int r = 0; r < 6; r++)
      if (r < 5 || wi < B_COUNT - 56) mbar_init(BAR(1 + 11 * r + wi), ((uint32_t)(bar_counts(r) >> (4 * wi)) & 15) + 1);
    asm volatile("fence.mbarrier_init.release.cluster;" ::: "memory");
  }
  if (tid == 0) STAMP(2, 6);
  asm volatile("barrier.cluster.arrive.relaxed.aligned;\nbarrier.cluster.wait.aligned;" ::: "memory");
  if (warp == 8 && elect_one()) {
    mbar_expect(BAR(B_FULL1), 16384);
    tma2d_mc(sb + 8192 + rank * 16384, &P.tmX0, 0, mb * 256 + 64 + rank * 128, BAR(B_FULL1));
  }
  if (tid == 256) STAMP(2, 7);

  if (warp < 8) {
    asm volatile("setmaxnreg.inc.sync.aligned.u32 224;");
    const int wg = warp >> 2, w = warp & 3, g = lane >> 2, q = lane & 3, t = tid & 127;
    const bool elect = (t == 0);
    const uint32_t s16 = (sb & 0x3FFFF) >> 4;
    uint32_t pq[2][16], ux[16], uh[16], X[4][2][8], H[4][2][8];
    ConvC K;
    const uint32_t dfl = s16 + (OFF_F2F >> 4) + (8 << 16), dil = s16 + (OFF_F2I >> 4) + (8 << 16), d4l = s16 + (OFF_F4 >> 4) + (8 << 16);
    const uint32_t xl = s16 + (OFF_XT >> 4) + 4 * wg * (XT_STRIDE >> 4) + (8 << 16);
    const uint32_t hl = s16 + (OFF_H >> 4) + wg * 512 + (8 << 16);
    {
      float acc[2][96];
      if (SPLIT0) {
#pragma unroll
        for (int mt = 0; mt < 2; mt++) {
          mbar_wait(BAR(mt ? B_FULL1 : B_FIRST), 0);
          if (mt == 0 && elect) { STAMP(wg, 1); GSTAMP(wg, 26); }
          wg_fence();
#pragma unroll
          for (int ks = 0; ks < 4; ks++)
            wgmma_ss_n192<0, 1>(acc[mt], dsc(s16 + wg * 1024 + mt * 512 + (1 << 16) + ks * 2, SW128), dsc(s16 + 2048 + (512 << 16) + ks * 128, SW128), ks != 0);
        }
        wg_commit();
      }
      int st = SPLIT0 ? 1 : 0, ph = 0;
#pragma unroll 1
      for (int kb = SPLIT0 ? 1 : 0; kb < 14; kb++) {
        mbar_wait(BAR(B_FULL1 + st), ph);
        if (kb == 0 && elect) { STAMP(wg, 1); GSTAMP(wg, 26); }
        if (kb == 8 && elect) { STAMP(wg, 16); GSTAMP(wg, 25); }
        const uint32_t da = s16 + st * (STAGE_BYTES >> 4) + wg * 1024 + (1 << 16);
        const uint32_t db = s16 + st * (STAGE_BYTES >> 4) + 2048 + (512 << 16);
        wg_fence();
#pragma unroll
        for (int ks = 0; ks < 4; ks++) {
          wgmma_ss_n192<0, 1>(acc[0], dsc(da + ks * 2, SW128), dsc(db + ks * 128, SW128), (kb | ks) != 0);
          wgmma_ss_n192<0, 1>(acc[1], dsc(da + 512 + ks * 2, SW128), dsc(db + ks * 128, SW128), (kb | ks) != 0);
        }
        wg_commit();
        wg_wait<1>();
        if (kb > 0 && t < 2) mbar_arrive_cl(BAR(B_EMPTY1 + (st == 0 ? 2 : st - 1)), t);
        if (++st == 3) { st = 0; ph ^= 1; }
      }
#define TAIL_MMA(mt, stage) do { wg_fence(); _Pragma("unroll") for (int ks = 0; ks < 4; ks++) \
        wgmma_ss_n192<0, 1>(acc[mt], dsc(s16 + (stage) * (STAGE_BYTES >> 4) + wg * 1024 + (mt) * 512 + (1 << 16) + ks * 2, SW128), \
                            dsc(s16 + (stage) * (STAGE_BYTES >> 4) + 2048 + (512 << 16) + ks * 128, SW128), 1); wg_commit(); } while (0)
      mbar_wait(BAR(B_FULL1 + 2), 0);
      TAIL_MMA(0, 2);
      wg_wait<1>();
      if (elect) mbar_arrive(BAR(B_SFREE));
      mbar_wait(BAR(B_FULL1 + 0), 1);
      TAIL_MMA(0, 0);
      TAIL_MMA(1, 2);
      const uint32_t lrow = sb + wg * 16384 + (16 * w + 8 * ((lane >> 3) & 1) + (lane & 7)) * 128 + (((lane >> 4) ^ (lane & 7)) << 4);
#define E1K(mt, i) do { if (opaque_true()) { _Pragma("unroll") for (int j = (i); j < (i) + 2; j++) { \
          const float* a = &acc[mt][32 + 8 * j]; const float* b = a + 32; const uint32_t o = (lrow ^ (j * 32)) + (mt) * 8192; \
          stsm4(o + 2 * STAGE_BYTES, pk2(b[0], b[1]), pk2(b[2], b[3]), pk2(b[4], b[5]), pk2(b[6], b[7])); \
          stsm4(o, phi2(a[0], a[1]), phi2(a[2], a[3]), phi2(a[4], a[5]), phi2(a[6], a[7])); } } } while (0)
#define E1Q(mt) do { if (opaque_true()) { _Pragma("unroll") for (int i = 0; i < 16; i++) pq[mt][i] = phi2(acc[mt][2 * i], acc[mt][2 * i + 1]); } } while (0)
#define LOAD_K() do { const uint4* ct = (const uint4*)P.thr + t; \
        _Pragma("unroll") for (int s = 0; s < 2; s++) { const uint4 u = ld_na4(ct + s * 128); K.a1[s][0] = u.x; K.a1[s][1] = u.y; K.a1[s][2] = u.z; K.a1[s][3] = u.w; } \
        const uint4 u = ld_na4(ct + 2 * 128); K.wa[0] = u.x; K.wa[1] = u.y; K.wb[0] = u.z; K.wb[1] = u.w; \
        K.sg = (lane & 4) ? 0xBC00BC00u : 0x3C003C00u; } while (0)
#define PK_READY(mt) do { fence_async(); __syncwarp(); if (lane == 0) mbar_arrive(BAR(B_PKRDY + (mt))); } while (0)
      wg_wait<1>();
      keep(acc[0]);
      if (elect) STAMP(wg, 18);
      E1K(0, 0);
      TAIL_MMA(1, 0);
      E1K(0, 2);
      if (elect) STAMP(wg, 19);
      PK_READY(0);
      wg_wait<0>();
      keep(acc[1]);
      if (elect) mbar_arrive(BAR(B_G1DONE));
      asm volatile("setmaxnreg.dec.sync.aligned.u32 200;");
      if (elect) { STAMP(wg, 2); GSTAMP(wg, 27); }
      E1K(1, 0);
      if (elect) STAMP(wg, 20);
      E1K(1, 2);
      if (elect) STAMP(wg, 21);
      PK_READY(1);
      if (elect) STAMP(wg, 3);
      LOAD_K();
      if (elect) STAMP(wg, 4);
      E1Q(0);
      E1Q(1);
      if (elect) STAMP(wg, 17);
      mbar_wait(BAR(B_H), 0);
      conv_m1(K, ux, xl);
      conv_m1(K, uh, hl);
      wg_wait<1>(); keepu(ux);
      if (lane == 0) mbar_arrive_cl(BAR(B_XFREE + 4 * wg), rank ^ 1);
      conv_s2(K, ux, X[0], dfl);
      wg_wait<1>(); keepu(uh);
      conv_s2(K, uh, H[0], dfl);
    }
    if (elect) STAMP(wg, 5);
    {
      uint32_t vst = sb + wg * 8192 + w * 512 + lane * 16, vld = sb + wg * 8192 + w * 2048 + lane * 16;
      uint32_t ya = mapa(sb + OFF_XT + 4 * wg * XT_STRIDE + (2 * rank + (w & 1)) * 1024 + lane * 16, w >> 1);
      const uint32_t ybar = mapa(BAR(B_Y), w >> 1);
      asm volatile("" : "+r"(vst), "+r"(vld), "+r"(ya));
      uint32_t W[2][8], V0[8], V1[8], y[8], a[4][4];
      uint4 ov[4];
      uint4* const ot = P.o + ((2 * mb + wg) * 16 + hq) * 1024 + (16 * w + g) * 8 + ((4 * rank + q) ^ g);
#define YOUT(i) do { if ((w >> 1) == rank) { \
          asm volatile("st.shared.v4.b32 [%0], {%1,%2,%3,%4};" ::"r"(ya + (i) * XT_STRIDE), "r"(y[0]), "r"(y[2]), "r"(y[4]), "r"(y[6]) : "memory"); \
          asm volatile("st.shared.v4.b32 [%0], {%1,%2,%3,%4};" ::"r"(ya + (i) * XT_STRIDE + 512), "r"(y[1]), "r"(y[3]), "r"(y[5]), "r"(y[7]) : "memory"); \
        } else { \
          mbar_wait(BAR(B_XFREE + 4 * wg + (i)), 0); \
          st_async4(ya + (i) * XT_STRIDE, y[0], y[2], y[4], y[6], ybar); \
          st_async4(ya + (i) * XT_STRIDE + 512, y[1], y[3], y[5], y[7], ybar); } } while (0)
      auto ocalc = [&](const int hh) {
        if (hh == 0) {
          if (elect) STAMP(wg, 8);
          mbar_wait(BAR(B_KV), 0);
          if (elect) STAMP(wg, 9);
        } else mbar_wait(BAR(B_KV1), 0);
        float oa[2][20];
        wg_fence();
#pragma unroll
        for (int m = 0; m < 4; m++) {
          const uint32_t* p = &pq[m & 1][8 * hh + 4 * (m >> 1)];
          wgmma_rs_n40<1>(oa[m & 1], p[0], p[1], p[2], p[3], dsc(s16 + (OFF_KVB >> 4) + hh * 160 + (m >> 1) * 16 + (8 << 16), 32), m >> 1);
        }
        wg_commit();
        wg_wait<0>();
#pragma unroll
        for (int mt = 0; mt < 2; mt++) {
          float (&o)[20] = oa[mt];
          keep(o);
          const uint32_t den = hadd(pk2(o[16], o[18]), 0x35863586u);
#pragma unroll
          for (int r = 0; r < 2; r++) {
            const float ri = rcp_fast(__uint_as_float(r ? (den & 0xFFFF0000u) : (den << 16)));
            uint4 u;
            u.x = pk2(o[2 * r] * ri, o[2 * r + 1] * ri);
            u.y = pk2(o[4 + 2 * r] * ri, o[5 + 2 * r] * ri);
            u.z = pk2(o[8 + 2 * r] * ri, o[9 + 2 * r] * ri);
            u.w = pk2(o[12 + 2 * r] * ri, o[13 + 2 * r] * ri);
            if (hh == 0) st_cg4(ot + (64 * mt + 8 * r) * 8, u); else ov[2 * mt + r] = u;
          }
        }
        if (hh == 0) {
          __syncwarp();
          if (lane == 0) mbar_arrive(BAR(B_ODONE));
          if (elect) STAMP(wg, 10);
        }
      };
      auto trickle = [&](const int qs) {
        const int m = qs - 2 * (OCH + O1D) - (TRICK - 1);
        if (m >= 0 && m < 4) {
          st_cg4(ot + 8 * 1024 + (64 * (m >> 1) + 8 * (m & 1)) * 8, ov[m]);
          if (m == 3) { __syncwarp(); if (lane == 0) mbar_arrive(BAR(B_ODONE1)); }
        }
      };
#pragma unroll
      for (int i = 0; i < 4; i++) {
        const bool nx = i < 3;
        const int n = nx ? i + 1 : i;
        const uint32_t vo = (i & 1) ? OFF_H + (i >> 1) * 16384 : OFF_VP;
        if (2 * i == OCH) ocalc(0);
        if (2 * i == OCH + O1D) ocalc(1);
        if (nx) {
          conv_m1(K, ux, xl + n * (XT_STRIDE >> 4));
          conv_m1(K, uh, hl + (n >> 1) * 1024 + (n & 1) * 256);
        }
        if (2 * i != OCH && 2 * i != OCH + O1D) { if (nx) { if (i > 0) wg_wait<3>(); else wg_wait<2>(); } else wg_wait<1>(); }
        keepu(X[i][0]); keepu(X[i][1]); keepu(H[i][0]); keepu(H[i][1]);
        conv_win(K, X[i], W);
        trickle(4 * i);
        conv_pw<0>(W, H[i], V0, dil);
        conv_pw<1>(W, H[i], V1, dil);
        trickle(4 * i + 1);
        wg_wait<2>();
        if (i > 0) { keepu(y); YOUT(i - 1); }
        if (2 * i + 1 == OCH) ocalc(0);
        if (2 * i + 1 == OCH + O1D) ocalc(1);
        if (nx) {
          keepu(ux); keepu(uh);
          if (lane == 0) mbar_arrive_cl(BAR(B_XFREE + 4 * wg + n), rank ^ 1);
          conv_s2(K, ux, X[n], dfl);
          wg_wait<1>();
        } else wg_wait<0>();
        keepu(V0); keepu(V1);
        trickle(4 * i + 2);
        if (i == 0) mbar_wait(BAR(B_H2), 0);
        conv_it<0>(K, V0, vst + vo);
        conv_it<1>(K, V1, vst + vo);
        bar_sync(1 + wg);
#pragma unroll
        for (int s = 0; s < 4; s++) ldsm4t(a[s], vld + vo + s * 512);
        if (nx) conv_s2(K, uh, H[n], dfl);
        conv_m4(y, a, d4l);
        trickle(4 * i + 3);
        if (i > 0 && lane < 2) mbar_arrive_cl(BAR(B_AFREE + i - 1), lane);
        if (elect && i < 3) STAMP(wg, i < 2 ? 6 + i : 9 + i);
      }
      wg_wait<0>(); keepu(y);
      YOUT(3);
      __syncwarp();
      if (lane == 0) mbar_arrive(BAR(B_Y));
      if (elect) STAMP(wg, 12);
    }
    {
      float acc[64];
#define G2_MMA(da, db, first) do { wg_fence(); _Pragma("unroll") for (int ks = 0; ks < 4; ks++) \
        wgmma_ss_n128<0, 1>(acc, dsc((da) + ks * 2, SW128), dsc((db) + ks * 128, SW128), ks || !(first)); wg_commit(); } while (0)
      const uint32_t a0 = s16 + wg * 512 + (1 << 16), b0 = s16 + (512 << 16);
      uint64_t ta = SLOT_A, tb = SLOT_B;
      uint32_t da = a0 + (SLOT_A & 15) * 1024, db = b0 + (SLOT_B & 15) * 1024, fb = BAR(B_FULL2);
      uint32_t cons = mapa(BAR(B_CONS2 - 1), t & 1);
      const bool rel = __shfl_sync(~0u, t, lane) < 2;
#pragma unroll 1
      for (int kb = 0; kb < HOLD2; kb++) {
        mbar_wait(fb, 0);
        if (kb == 0 && elect) { STAMP(wg, 13); GSTAMP(wg, 28); }
        G2_MMA(da, db, kb == 0);
        ta >>= 4; tb >>= 4;
        da = a0 + ((uint32_t)ta & 15) * 1024; db = b0 + ((uint32_t)tb & 15) * 1024; fb += 8;
        asm volatile("" : "+r"(da), "+r"(db));
        wg_wait<1>();
        if (kb > 0 && kb < 12 && rel) asm volatile("mbarrier.arrive.shared::cluster.b64 _, [%0];" ::"r"(cons) : "memory");
        cons += 8;
      }
#pragma unroll
      for (int kb = HOLD2; kb < 16; kb++) {
        if (wg == 1) mbar_wait(BAR(B_FULL2 + kb), 0);
        else if (kb == HOLD2) asm volatile("bar.sync 3, 256;" ::: "memory");
        G2_MMA(a0 + ((SLOT_A >> (4 * kb)) & 15) * 1024, b0 + ((SLOT_B >> (4 * kb)) & 15) * 1024, false);
      }
      if (wg == 1) asm volatile("bar.arrive 3, 256;" ::: "memory");
      const uint32_t stg = sb + wg * 8192 + w * 2048, so0 = ((SLOT_A >> 56) & 15) * 16384, so1 = ((SLOT_A >> 60) & 15) * 16384;
      const uint32_t lrow = stg + (8 * ((lane >> 3) & 1) + (lane & 7)) * 128 + (((lane >> 4) ^ (lane & 7)) << 4);
      const int col = 1024 + 256 * cb + 128 * rank, row = 128 * rb + 64 * wg + 16 * w;
      wg_wait<0>();
      keep(acc);
      if (elect) { STAMP(wg, 14); GSTAMP(wg, 29); }
#pragma unroll
      for (int cp = 0; cp < 8; cp++) {
        const float* a = &acc[8 * cp];
        stsm4((lrow ^ ((cp & 3) * 32)) + (cp >> 2 ? so1 : so0), pk2(a[0], a[1]), pk2(a[2], a[3]), pk2(a[4], a[5]), pk2(a[6], a[7]));
        if ((cp & 3) == 3) {
          fence_async();
          __syncwarp();
          if (elect_one()) tma2d_st(&P.tmOB, stg + (cp >> 2 ? so1 : so0), col + (cp >> 2) * 64, row);
        }
      }
      asm volatile("cp.async.bulk.commit_group;\ncp.async.bulk.wait_group.read 0;" ::: "memory");
      if (elect) {
        STAMP(wg, 15); GSTAMP(wg, 31); PDUMP(wg); if (wg == 0) PDUMP(2);
      }
    }
  } else {
    asm volatile("setmaxnreg.dec.sync.aligned.u32 56;");
    const int hw = warp - 9, g = lane >> 2, q = lane & 3;
#define sbar (bars + 8 * (B_STG - 18) + 16 * warp)
    if (warp == 8) {
      if (D1) __nanosleep(D1);
      int st = 1, pp = 1;
      const uint8_t* pfx = (const uint8_t*)P.x + (mb * 256 + hp * 16 + (lane & 15)) * 2048;
      const uint8_t* pfw = (const uint8_t*)P.w + (mb * 8 + (lane & 7)) * 6144 + (lane >> 3) * 2048 + hp * 128;
#pragma unroll 1
      for (int kb = 1; kb < 16; kb++) {
        if (kb >= 3) mbar_wait(BAR(B_EMPTY1 + st), pp);
        const uint32_t sa = sb + st * STAGE_BYTES;
        if (elect_one()) {
          mbar_expect(BAR(B_FULL1 + st), STAGE_BYTES);
          tma2d_mc(sa + rank * 16384, &P.tmX, kb * 64, mb * 256 + rank * 128, BAR(B_FULL1 + st));
          tma3d(sa + 32768, &P.tmW, hp * 64, kb * 64, 0, BAR(B_FULL1 + st));
        }
        if (kb == 1 && lane == 0) STAMP(2, 24);
        if (PFD && kb >= 2) {
#pragma unroll 1
          for (int j = kb == 2 ? 3 : kb + PFD; j <= kb + PFD && j < 16; j++) {
            if (lane < 16) asm volatile("prefetch.global.L2 [%0];" ::"l"(pfx + j * 128));
            if (lane < 24) asm volatile("prefetch.global.L2 [%0];" ::"l"(pfw + j * (64 * 6144)));
          }
          if (kb >= QPF && kb < QPF + 8) asm volatile("prefetch.global.L2 [%0];" ::"l"((const uint8_t*)P.q + (blockIdx.x * 256 + (kb - QPF) * 32 + lane) * 128));
          if (kb >= 4)
            asm volatile("prefetch.global.L2 [%0];" ::"l"(kb < 12 ? (const uint8_t*)P.h + ((2 * cl + rank) * 256 + (kb - 4) * 32 + lane) * 128
                                                                  : (const uint8_t*)P.wo + (blockIdx.x * 128 + (kb - 12) * 32 + lane) * 128));
        }
        if (++st == 3) { st = 0; pp ^= 1; }
      }
      if (lane == 0) STAMP(2, 1);
    } else {
      {
        const uint32_t clk0 = __shfl_sync(~0u, (uint32_t)clock(), 0), stg = sb + OFF_STG + hw * STG_STRIDE;
        const unsigned epoch = __shfl_sync(~0u, P.epoch[blockIdx.x], 0);
        const uint32_t tag = ~epoch & 1;
        uint32_t tap[2][4];
#pragma unroll
        for (int cg = 0; cg < 2; cg++) {
          const uint2 u = __ldg((const uint2*)(P.shift_k + (16 * cl + 8 * cg + g) * 4));
          tap[cg][0] = __byte_perm(u.x, 0, 0x1010); tap[cg][1] = __byte_perm(u.x, 0, 0x3232);
          tap[cg][2] = __byte_perm(u.y, 0, 0x1010); tap[cg][3] = __byte_perm(u.y, 0, 0x3232);
        }
        if (hw == 0 && lane < 8) *(float*)(smem + OFF_D + 4 * lane) = __bfloat162float(P.D[16 * cl + 8 * rank + lane]);
        if (hw == 1 && lane < 24) asm volatile("prefetch.global.L2 [%0];" ::"l"(P.thr + (lane + 24 * rank) * 32));
        if (hw == 0 && elect_one()) {
          *(volatile unsigned*)(smem + OFF_EPOCH) = epoch;
          mbar_expect(BAR(B_XRAW), 16384);
          mbar_expect(BAR(B_Y), 16384 + 64);
        }
        for (int i = hw * 32 + lane; i < 528; i += 96) st_tag4(P.part + (hp * 8 + mb) * 2176 + 4 * i, 0.f, 0.f, 0.f, 0.f, tag ^ 1);
        if (hw < 2 || lane < 2) st_tag4(P.kv + hp * 2176 + (4 * (hw < 2 ? 64 * mb + 32 * hw + lane : 512 + 8 * (mb & 1) + (mb & 6) + lane)), 0.f, 0.f, 0.f, 0.f, tag ^ 1);
        if (lane == 0) STAMP(3, hw);
        const uint32_t xo = sb + OFF_XT + g * XT_STRIDE + rank * 2048 + q * 4;
        const int krow = 8 + (lane & 7) - (lane >> 3);
        const uint32_t ka = stg + krow * 32 + ((krow & 4) << 2), va = stg + 2304 + lane * 32 + ((lane & 4) << 2);
        int ph = 0, b = 0;
#pragma unroll 1
        for (int ci = hw - 3; ci < 16; ci += 3) {
          const uint32_t bo = b ? OFF_F2F - OFF_STG : 0, bn = b ? 0 : OFF_F2F - OFF_STG;
          if (ci + 3 < 16) {
            while (__any_sync(~0u, (uint32_t)clock() - clk0 < HSTART + (ci + 3) * PACE)) __nanosleep(64);
            if (elect_one()) {
              mbar_expect(sbar + 8 * (b ^ 1), 2304 + 2048);
              tma2d(stg + bn, &P.tmK, 16 * cl, 1024 * rank + 64 * (ci + 3) - 8, sbar + 8 * (b ^ 1));
              tma2d(stg + bn + 2304, &P.tmV, 16 * cl, 1024 * rank + 64 * (ci + 3), sbar + 8 * (b ^ 1));
            }
          }
          if (ci >= 0) {
            mbar_wait(sbar + 8 * b, (ph >> b) & 1);
            ph ^= 1 << b;
#pragma unroll 1
            for (int grp = 0; grp < 2; grp++) {
#pragma unroll
              for (int cg = 0; cg < 2; cg++) {
                const uint32_t dst = mapa(xo + (ci >> 3) * 1024 + ((ci & 7) * 4 + 2 * grp) * 16, cg), xbar = mapa(BAR(B_XRAW), cg);
                uint32_t vv[4], kk[4][4];
                ldsm4t(vv, (va ^ (cg * 16)) + bo + grp * 1024);
#pragma unroll
                for (int rg = 0; rg < 4; rg++) ldsm4t(kk[rg], (ka ^ (cg * 16)) + bo + grp * 1024 + rg * 256);
#pragma unroll
                for (int rg = 0; rg < 4; rg++)
                  vv[rg] = hmul(hadd(hadd(hadd(hmul(kk[rg][3], tap[cg][3]), hmul(kk[rg][2], tap[cg][2])), hmul(kk[rg][1], tap[cg][1])), hmul(kk[rg][0], tap[cg][0])), vv[rg]);
                if (cg == rank) {
#pragma unroll
                  for (int rg = 0; rg < 4; rg++) asm volatile("st.shared.b32 [%0], %1;" ::"r"(dst + (rg & 1) * 512 + (rg >> 1) * 16), "r"(vv[rg]) : "memory");
                } else {
#pragma unroll
                  for (int rg = 0; rg < 4; rg++) st_async(dst + (rg & 1) * 512 + (rg >> 1) * 16, vv[rg], xbar);
                }
              }
            }
          }
          b ^= 1;
        }
      }
      if (lane == 0) STAMP(3, 3 + hw);
      asm volatile("bar.sync 4, 96;" ::: "memory");
      if (hw == 0 && elect_one()) { mbar_expect(BAR(B_XT), 10240); bulk_ld(sb + OFF_F2F, P.img, 10240, BAR(B_XT)); }
      mbar_wait(BAR(B_XRAW), 0);
    }
    int e1 = 0;
#pragma unroll 1
    for (int n = hw < 0 ? 3 : 0; n < 4; n++) {
      const bool isH = n >= 3;
      const int c = isH ? (warp & 1) + 2 * (warp & 2) : hw + 3 * n;
      if (c < 8) {
        int ln;
        asm volatile("mov.u32 %0, %%laneid;" : "=r"(ln));
        uint8_t* dst = smem + (isH ? OFF_H + (c & 2) * 8192 + (c >> 2) * 8192 + (c & 1) * 4096 : OFF_XT + c * XT_STRIDE) + ((ln >> 4) * 512 + (ln & 15) * 16);
        const uint8_t* src0 = isH ? (const uint8_t*)P.h + (16 * cl + 8 * rank + c) * 4096 + ((ln & 15) * 32 + (ln & 16)) : dst;
        const uint8_t* src1 = src0 + (isH ? 512 : 256);
        uint32_t v[32];
#pragma unroll
        for (int i = 0; i < 8; i++) {
          const uint4 u = *(const uint4*)(((i & 1) ? src1 : src0) + (i >> 1) * 1024);
          v[4 * i] = u.x; v[4 * i + 1] = u.y; v[4 * i + 2] = u.z; v[4 * i + 3] = u.w;
        }
        if (isH) mbar_wait(BAR(B_XT), 0);
        const float f0 = __uint_as_float(v[0] << 16) + ((isH && ln == 0) ? *(const float*)(smem + OFF_D + 4 * c) : 0.f);
        const int e = norm_exp(v, f0);
        norm_cvt(v, f0, e);
        if (isH) mbar_wait(BAR(B_SFREE), 0);
        else if (ln == 0) smem[OFF_EX + c] = e;
        e1 = e;
#pragma unroll
        for (int i = 0; i < 8; i++)
          *(uint4*)(dst + (i >> 1) * 1024 + (i & 1) * 256) = make_uint4(v[4 * i], v[4 * i + 1], v[4 * i + 2], v[4 * i + 3]);
        if (n < 2 && elect_one()) {
          if (n == 0) mbar_expect(sbar, 4096);
          tma3d(sb + OFF_STG + 2048 * c, &P.tmQ, 16 * cl, 64 * rank, 2 * c, sbar);
        }
      }
      if (n >= 2) {
        fence_async();
        __syncwarp();
        if (lane == 0) { mbar_arrive(BAR(isH ? B_H : B_XT)); STAMP(3, (isH ? 17 : 13) + hw); }
      }
    }
#define SLOT(tab, kb) (sb + ((uint32_t)((tab) >> (4 * (kb))) & 15) * 16384)
#define LOAD_B(kb) tma4d(SLOT(SLOT_B, kb), &P.tmWo, 0, ((kb) >> 3) * 32, 2 * ((kb) & 7), 4 * cb + 2 * rank, BAR(B_FULL2 + (kb)))
#define LOAD_A(kb) bulk_ld_mc(SLOT(SLOT_A, kb) + rank * 8192, P.o + (rb * 16 + (kb)) * 1024 + rank * 512, 8192, BAR(B_FULL2 + (kb)))
    asm volatile("setmaxnreg.inc.sync.aligned.u32 104;");
    {
    int tid;
    asm volatile("mov.u32 %0, %%tid.x;" : "=r"(tid));
    const int lane = tid & 31, g = lane >> 2, q = lane & 3;
    const unsigned epoch = *(volatile unsigned*)(smem + OFF_EPOCH);
    const uint32_t tag = ~epoch & 1;
    const int pi = hw < 2 ? 64 * mb - 288 + tid : 512 + 8 * (mb & 1) + (mb & 6) + (lane & 1);
    const float* psrc = P.part + hp * 8 * 2176 + 4 * pi;
    uint4 f[8];
    {
      const uint32_t s16 = (sb & 0x3FFFF) >> 4;
      const int t = tid & 127, c = 2 + (warp & 1) + 2 * (warp & 2);
      const uint4* hp4 = (const uint4*)(P.h + (16 * cl + 8 * rank + c) * 2048) + ((lane & 15) * 2 + (lane >> 4));
      uint32_t v[32];
#pragma unroll
      for (int i = 0; i < 8; i++) { const uint4 u = ld_na4(hp4 + i * 32); v[4 * i] = u.x; v[4 * i + 1] = u.y; v[4 * i + 2] = u.z; v[4 * i + 3] = u.w; }
      float kva[36];
#pragma unroll
      for (int mt = 0; mt < 2; mt++) {
        mbar_wait(BAR(B_PKRDY + mt), 0);
        wg_fence();
#pragma unroll
        for (int ks = 0; ks < 8; ks++) {
          const uint32_t o = (ks >> 2) * 1024 + mt * 512 + (ks & 3) * 128, vb = (2 * STAGE_BYTES >> 4) + o;
          wgmma_ss_n72<1, 1>(kva, dsc(s16 + o + (1 << 16), SW128), dsc(s16 + vb + (((OFF_ONES >> 4) - vb) << 16), SW128), (mt | ks) != 0);
        }
        wg_commit();
        if (mt == 0 && hw < 0) {
          mbar_wait(BAR(B_G1DONE), 0);
          if (elect_one()) {
#pragma unroll
            for (int kb = 0; kb < BEARLY; kb++) { mbar_expect(BAR(B_FULL2 + kb), 16384); LOAD_B(kb); }
          }
        }
      }
      float* pdst = P.part + (hp * 8 + mb) * 2176 + t * 4;
      float* zdst = P.part + (hp * 8 + mb) * 2176 + 2048 + (t >> 1);
      asm volatile("" : "+l"(pdst), "+l"(zdst));
      wg_wait<0>();
      keep(kva);
      if (hw < 1) {
#pragma unroll
        for (int c = 0; c < 4; c++) st_tag4(pdst + c * 512, kva[4 * c], kva[4 * c + 1], kva[4 * c + 2], kva[4 * c + 3], tag);
      } else {
#pragma unroll
        for (int c = 4; c < 8; c++) st_tag4(pdst + (c - 4) * 512, kva[4 * c], kva[4 * c + 1], kva[4 * c + 2], kva[4 * c + 3], tag);
      }
      const float z2 = __shfl_down_sync(~0u, kva[32], 4), z3 = __shfl_down_sync(~0u, kva[34], 4);
      if (!(lane & 7)) st_tag4(zdst, kva[32], kva[34], z2, z3, tag);
      if (lane == 0) mbar_arrive(BAR(B_PKFREE));
      const uint32_t cst = clock();
      if (hw == 0 && lane == 0) STAMP(3, 24);
      const float f0 = __uint_as_float(v[0] << 16) + (lane == 0 ? *(const float*)(smem + OFF_D + 4 * c) : 0.f);
      const int e = norm_exp(v, f0);
      norm_cvt(v, f0, e);
      if (hw >= 0) {
        while (__any_sync(~0u, (uint32_t)clock() - cst < PD1)) __nanosleep(20);
        if (hw == 0 && lane == 0) STAMP(3, 20);
#pragma unroll
        for (int p = 0; p < 8; p++) f[p] = ld_rlx4(psrc + p * 2176);
      }
      uint8_t* dst = smem + OFF_H + 16384 + (warp & 3) * 4096 + (lane >> 4) * 512 + (lane & 15) * 16;
#pragma unroll
      for (int i = 0; i < 8; i++)
        *(uint4*)(dst + (i >> 1) * 1024 + (i & 1) * 256) = make_uint4(v[4 * i], v[4 * i + 1], v[4 * i + 2], v[4 * i + 3]);
      if (lane < 4) {
        const int cc = c - (lane & 2);
        st_async(mapa(sb + OFF_SCALE + (8 * rank + cc) * 4, lane & 1), min(max(((lane & 2) ? e1 : e) + smem[OFF_EX + cc] - 124, 1), 254) << 23, mapa(BAR(B_Y), lane & 1));
      }
    }
#define H2_READY() do { fence_async(); __syncwarp(); if (lane == 0) mbar_arrive(BAR(B_H2)); } while (0)
    if (warp == 8) {
      H2_READY();
      mbar_wait(BAR(B_PKFREE), 0);
      {
        const uint32_t c0 = clock();
#pragma unroll 1
        for (int i = 0; i < 2 * NPRE - 2 * BEARLY; i++) {
          const int kb = (i >> 1) + BEARLY;
          while (__any_sync(~0u, (uint32_t)clock() - c0 < i * BPACE)) __nanosleep(32);
          if (elect_one()) {
            if (!(i & 1)) mbar_expect(BAR(B_FULL2 + kb), 16384);
            tma4d(SLOT(SLOT_B, kb) + (i & 1) * 8192, &P.tmWo1, 0, 0, 2 * kb, 4 * cb + 2 * rank + (i & 1), BAR(B_FULL2 + kb));
            if (i == 0) mbar_expect(BAR(B_Q), 8192);
            if (i < 4) tma3d(sb + OFF_SPARE + 2048 * i, &P.tmQ, 16 * cl, 64 * rank + 32 * (i >> 1), 2 * ((i + 6) & 7), BAR(B_Q));
          }
        }
      }
      if (lane == 0) STAMP(2, 2);
      mbar_wait(BAR(B_AFREE), 0);
      if (elect_one()) mbar_expect(BAR(B_FULL2), 16384);
      {
        const uint32_t dst = SLOT(SLOT_A, 0) + rank * 8192;
        const uint4* src = P.o + rb * 16 * 1024 + rank * 512;
        poll_ge(&P.ocnt[rb * 32], 16 * (epoch + 1));
        asm volatile("fence.proxy.async.global;" ::: "memory");
        if (lane == 0) STAMP(2, 3);
        if (elect_one()) bulk_ld_mc(dst, src, 8192, BAR(B_FULL2));
        if (lane == 0) STAMP(3, 23);
      }
#pragma unroll 1
      for (int kb = 1; kb < NPRE; kb++) {
        mbar_wait(BAR(kb < 4 ? B_AFREE + kb - 1 : B_CONS2), 0);
        if (elect_one()) { mbar_expect(BAR(B_FULL2 + kb), 16384); LOAD_A(kb); }
      }
#pragma unroll 1
      for (int kb = NPRE; kb < 16; kb++) {
        mbar_wait(BAR(B_CONS2 + kb - 5), 0);
        if (kb == 8) mbar_wait(BAR(B_O1RDY), 0);
        if (elect_one()) { mbar_expect(BAR(B_FULL2 + kb), 32768); LOAD_A(kb); LOAD_B(kb); }
      }
      if (lane == 0) { P.epoch[blockIdx.x] = epoch + 1; STAMP(2, 5); }
    } else {
      {
#pragma unroll 1
        for (int n = 0; __any_sync(~0u, stale8(f, tag) & 1); n++) {
#pragma unroll
          for (int p = 0; p < 8; p++) ld_stale4(f[p], psrc + p * 2176, tag);
          if (n > SPIN_LIMIT) __trap();
        }
        float s0 = 0.f, s1 = 0.f, s2 = 0.f, s3 = 0.f;
#pragma unroll
        for (int p = 0; p < 8; p++) { s0 += __uint_as_float(f[p].x); s1 += __uint_as_float(f[p].y); s2 += __uint_as_float(f[p].z); s3 += __uint_as_float(f[p].w); }
        if (hw < 2 || lane < 2) st_tag4(P.kv + hp * 2176 + (4 * pi), s0, s1, s2, s3, tag);
      }
      const uint32_t cs2 = clock();
      if (lane == 0 && hw == 0) STAMP(3, 8);
      H2_READY();
      if (hw == 2) {
        unsigned* cnt = P.ocnt + (2 * mb + lane) * 32;
#pragma unroll 1
        for (int hh = 0; hh < 2; hh++) {
          mbar_wait(BAR(hh ? B_ODONE1 : B_ODONE), 0);
          if (lane < 2) asm volatile("red.release.gpu.global.add.u32 [%0], 1;" ::"l"(cnt) : "memory");
          cnt += 512;
          if (lane == 0) STAMP(3, hh ? 6 : 7);
        }
        poll_ge(&P.ocnt[512 + rb * 32], 16 * (epoch + 1));
        asm volatile("fence.proxy.async.global;" ::: "memory");
        if (lane == 0) { mbar_arrive(BAR(B_O1RDY)); STAMP(2, 4); }
        __syncwarp();
      } else {
        const int t = tid - 288;
        const float* src = P.kv + hp * 2176 + 4 * (t + 32 * hw);
        const float* zsrc = P.kv + hp * 2176 + (2048 + (t & 48) + 2 * (lane & 6));
        mbar_wait(BAR(B_PKFREE), 0);
        while (__any_sync(~0u, (uint32_t)clock() - cs2 < PD2)) __nanosleep(20);
        uint4 zp = ld_rlx4(zsrc);
#pragma unroll
        for (int p = 0; p < 8; p++) f[p] = ld_rlx4(src + 4 * ((p & 3) * 128 + (p >> 2) * 32));
        if (!opaque_true()) __trap();
#pragma unroll 1
        for (int n = 0; __any_sync(~0u, (stale8(f, tag) | (zp.x ^ tag)) & 1); n++) {
          ld_stale4(zp, zsrc, tag);
#pragma unroll
          for (int p = 0; p < 8; p++) ld_stale4(f[p], src + 4 * ((p & 3) * 128 + (p >> 2) * 32), tag);
          if (n > SPIN_LIMIT) __trap();
        }
#define PK2U(a, b) pk2(__uint_as_float(a), __uint_as_float(b))
        const uint32_t zf = (lane & 1) ? ((lane & 8) ? zp.w : zp.z) : ((lane & 8) ? zp.y : zp.x);
        const uint32_t zz = PK2U(zf, zf);
        *(uint4*)(smem + OFF_KVB + hw * 2560 + 2048 + lane * 16) = make_uint4(zz, zz, zz, zz);
#pragma unroll
        for (int hh = 0; hh < 2; hh++) {
          const uint4* ff = &f[4 * hh];
          uint8_t* dst = smem + OFF_KVB + hw * 2560 + q * 512 + (16 * hh + g) * 16;
          *(uint4*)dst = make_uint4(PK2U(ff[0].x, ff[0].y), PK2U(ff[1].x, ff[1].y), PK2U(ff[2].x, ff[2].y), PK2U(ff[3].x, ff[3].y));
          *(uint4*)(dst + 128) = make_uint4(PK2U(ff[0].z, ff[0].w), PK2U(ff[1].z, ff[1].w), PK2U(ff[2].z, ff[2].w), PK2U(ff[3].z, ff[3].w));
        }
        fence_async();
        __syncwarp();
        if (lane == 0) { mbar_arrive(BAR(hw ? B_KV1 : B_KV)); if (hw == 0) STAMP(3, 9); }
      }
#define QBUF(ci) (sb + 2048 * (ci) + ((ci) < 6 ? OFF_STG : (ci) < 10 ? OFF_SPARE - 6 * 2048 : OFF_F2F - 10 * 2048))
      mbar_wait(BAR(B_Y), 0);
      if (elect_one()) {
        mbar_expect(sbar + 8, 4096);
#pragma unroll 1
        for (int ci = hw ? hw + 9 : 12; ci < 16; ci += 3) tma3d(QBUF(ci), &P.tmQ, 16 * cl, 64 * rank + 32, 2 * (ci & 7), sbar + 8);
      }
      mbar_wait(BAR(B_Q), 0);
      mbar_wait(sbar, hw == 0);
      {
        const float2 sc0 = *(const float2*)(smem + OFF_SCALE + 8 * q), sc1 = *(const float2*)(smem + OFF_SCALE + 32 + 8 * q);
        const uint32_t yl = sb + OFF_XT + (lane & 7) * XT_STRIDE + (lane >> 3) * 16;
#pragma unroll 1
        for (int ci = hw; ci < 16; ci += 3) {
          const uint32_t qb = QBUF(ci);
          if (ci >= 10) mbar_wait(sbar + 8, 1);
#pragma unroll 1
          for (int nl = 0; nl < 2; nl++) {
            uint32_t yy[2][4], qq[2][4];
            const uint32_t qa = qb + lane * 32 + ((lane & 4) << 2) + nl * 1024;
#pragma unroll
            for (int cg = 0; cg < 2; cg++) { ldsm4t(yy[cg], yl + cg * 2048 + (2 * ci + nl) * 64); ldsm4(qq[cg], qa ^ (cg * 16)); }
#pragma unroll
            for (int cg = 0; cg < 2; cg++) {
              const float2 sc = cg ? sc1 : sc0;
#pragma unroll
              for (int m = 0; m < 4; m++) {
                const float2 f = __half22float2(*(const __half2*)&yy[cg][m]);
                qq[cg][m] = hmul(qq[cg][m], pk2(f.x * sc.x, f.y * sc.y));
              }
              stsm4(qa ^ (cg * 16), qq[cg][0], qq[cg][1], qq[cg][2], qq[cg][3]);
            }
          }
          fence_async();
          __syncwarp();
          if (elect_one()) tma3d_st(&P.tmOA, qb, 16 * cl, 64 * rank + 32 * (ci >> 3), 2 * (ci & 7));
        }
        asm volatile("cp.async.bulk.commit_group;\ncp.async.bulk.wait_group.read 0;" ::: "memory");
      }
      if (lane == 0) STAMP(3, 10 + hw);
    }
    }
  }
}

typedef CUresult (*EncodeFn)(CUtensorMap*, CUtensorMapDataType, cuuint32_t, void*, const cuuint64_t*, const cuuint64_t*,
                             const cuuint32_t*, const cuuint32_t*, CUtensorMapInterleave, CUtensorMapSwizzle,
                             CUtensorMapL2promotion, CUtensorMapFloatOOBfill);

static void enc(EncodeFn fn, CUtensorMap* m, const void* p, int rank, const cuuint64_t* dims, const cuuint64_t* strides,
                const cuuint32_t* box, CUtensorMapSwizzle swz, CUtensorMapL2promotion promo) {
  cuuint32_t es[4] = {1, 1, 1, 1};
  fn(m, CU_TENSOR_MAP_DATA_TYPE_BFLOAT16, rank, (void*)p, dims, strides, box, es, CU_TENSOR_MAP_INTERLEAVE_NONE, swz, promo,
     CU_TENSOR_MAP_FLOAT_OOB_FILL_NONE);
}

extern "C" void kernel_launch(void* const* d_in, const int* in_sizes, int n_in, void* d_out, int out_size) {
  void* fp = nullptr;
  cudaDriverEntryPointQueryResult qr;
  cudaGetDriverEntryPoint("cuTensorMapEncodeTiled", &fp, cudaEnableDefault, &qr);
  EncodeFn fn = (EncodeFn)fp;
  Params P;
  P.shift_k = (const __nv_bfloat16*)d_in[3]; P.h = (const __nv_bfloat16*)d_in[4]; P.D = (const __nv_bfloat16*)d_in[5];
  P.q = (const __nv_bfloat16*)d_in[0];
  cudaGetSymbolAddress((void**)&P.part, g_part); cudaGetSymbolAddress((void**)&P.kv, g_kv); cudaGetSymbolAddress((void**)&P.o, g_o);
  cudaGetSymbolAddress((void**)&P.ocnt, g_ocnt); cudaGetSymbolAddress((void**)&P.epoch, g_epoch);
  cudaGetSymbolAddress((void**)&P.thr, c_thr); cudaGetSymbolAddress((void**)&P.img, c_img);
  P.x = (const __nv_bfloat16*)d_in[6]; P.w = (const __nv_bfloat16*)d_in[7]; P.wo = (const __nv_bfloat16*)d_in[8];
  const CUtensorMapSwizzle S128 = CU_TENSOR_MAP_SWIZZLE_128B, S32 = CU_TENSOR_MAP_SWIZZLE_32B;
  const CUtensorMapL2promotion P0 = CU_TENSOR_MAP_L2_PROMOTION_NONE, P128 = CU_TENSOR_MAP_L2_PROMOTION_L2_128B;
  { cuuint64_t d[2] = {1024, 2048}, s[1] = {2048}; cuuint32_t b[2] = {64, 128}; enc(fn, &P.tmX, d_in[6], 2, d, s, b, S128, P128); }
  { cuuint64_t d[2] = {1024, 2048}, s[1] = {2048}; cuuint32_t b[2] = {64, 64}; enc(fn, &P.tmX0, d_in[6], 2, d, s, b, S128, P128); }
  { cuuint64_t d[3] = {1024, 1024, 3}, s[2] = {6144, 2048}; cuuint32_t b[3] = {64, 64, 3}; enc(fn, &P.tmW, d_in[7], 3, d, s, b, S128, P128); }
  { cuuint64_t d[4] = {64, 64, 16, 16}, s[3] = {2048, 131072, 128}; cuuint32_t b[4] = {64, 32, 2, 2}; enc(fn, &P.tmWo, d_in[8], 4, d, s, b, S128, P128); }
  { cuuint64_t d[4] = {64, 64, 16, 16}, s[3] = {2048, 131072, 128}; cuuint32_t b[4] = {64, 32, 2, 1}; enc(fn, &P.tmWo1, d_in[8], 4, d, s, b, S128, P128); }
  { cuuint64_t d[2] = {1024, 2048}, s[1] = {2048}; cuuint32_t b[2] = {16, 72}; enc(fn, &P.tmK, d_in[1], 2, d, s, b, S32, P128); }
  { cuuint64_t d[2] = {1024, 2048}, s[1] = {2048}; cuuint32_t b[2] = {16, 64}; enc(fn, &P.tmV, d_in[2], 2, d, s, b, S32, P128); }
  { cuuint64_t d[3] = {1024, 128, 16}, s[2] = {32768, 2048}; cuuint32_t b[3] = {16, 32, 2}; enc(fn, &P.tmQ, d_in[0], 3, d, s, b, S32, P128); }
  { cuuint64_t d[3] = {1024, 128, 16}, s[2] = {65536, 4096}; cuuint32_t b[3] = {16, 32, 2}; enc(fn, &P.tmOA, d_out, 3, d, s, b, S32, P0); }
  { cuuint64_t d[2] = {2048, 2048}, s[1] = {4096}; cuuint32_t b[2] = {64, 16}; enc(fn, &P.tmOB, d_out, 2, d, s, b, S128, P0); }
  cudaFuncSetAttribute(fused_kernel, cudaFuncAttributeMaxDynamicSharedMemorySize, SMEM_TOTAL);
  fused_kernel<<<128, 384, SMEM_TOTAL>>>(P);
}
```

```cpp
#include <cuda_runtime.h>
#include <cuda_bf16.h>
#include <cuda_fp16.h>
#include <cuda.h>
#include <stdint.h>

template<int TA, int TB, int SA=1> __device__ __forceinline__ void wgmma_ss_n192(float (&d)[96], uint64_t da, uint64_t db, int scale_d) {
  asm volatile("{\n.reg .pred p;\nsetp.ne.b32 p, %98, 0;\n"
    "wgmma.mma_async.sync.aligned.m64n192k16.f32.bf16.bf16 {%0, %1, %2, %3, %4, %5, %6, %7, %8, %9, %10, %11, %12, %13, %14, %15, %16, %17, %18, %19, %20, %21, %22, %23, %24, %25, %26, %27, %28, %29, %30, %31, %32, %33, %34, %35, %36, %37, %38, %39, %40, %41, %42, %43, %44, %45, %46, %47, %48, %49, %50, %51, %52, %53, %54, %55, %56, %57, %58, %59, %60, %61, %62, %63, %64, %65, %66, %67, %68, %69, %70, %71, %72, %73, %74, %75, %76, %77, %78, %79, %80, %81, %82, %83, %84, %85, %86, %87, %88, %89, %90, %91, %92, %93, %94, %95}, %96, %97, p, %101, 1, %99, %100;\n}\n"
    : "+f"(d[0]), "+f"(d[1]), "+f"(d[2]), "+f"(d[3]), "+f"(d[4]), "+f"(d[5]), "+f"(d[6]), "+f"(d[7]), "+f"(d[8]), "+f"(d[9]), "+f"(d[10]), "+f"(d[11]), "+f"(d[12]), "+f"(d[13]), "+f"(d[14]), "+f"(d[15]), "+f"(d[16]), "+f"(d[17]), "+f"(d[18]), "+f"(d[19]), "+f"(d[20]), "+f"(d[21]), "+f"(d[22]), "+f"(d[23]), "+f"(d[24]), "+f"(d[25]), "+f"(d[26]), "+f"(d[27]), "+f"(d[28]), "+f"(d[29]), "+f"(d[30]), "+f"(d[31]), "+f"(d[32]), "+f"(d[33]), "+f"(d[34]), "+f"(d[35]), "+f"(d[36]), "+f"(d[37]), "+f"(d[38]), "+f"(d[39]), "+f"(d[40]), "+f"(d[41]), "+f"(d[42]), "+f"(d[43]), "+f"(d[44]), "+f"(d[45]), "+f"(d[46]), "+f"(d[47]), "+f"(d[48]), "+f"(d[49]), "+f"(d[50]), "+f"(d[51]), "+f"(d[52]), "+f"(d[53]), "+f"(d[54]), "+f"(d[55]), "+f"(d[56]), "+f"(d[57]), "+f"(d[58]), "+f"(d[59]), "+f"(d[60]), "+f"(d[61]), "+f"(d[62]), "+f"(d[63]), "+f"(d[64]), "+f"(d[65]), "+f"(d[66]), "+f"(d[67]), "+f"(d[68]), "+f"(d[69]), "+f"(d[70]), "+f"(d[71]), "+f"(d[72]), "+f"(d[73]), "+f"(d[74]), "+f"(d[75]), "+f"(d[76]), "+f"(d[77]), "+f"(d[78]), "+f"(d[79]), "+f"(d[80]), "+f"(d[81]), "+f"(d[82]), "+f"(d[83]), "+f"(d[84]), "+f"(d[85]), "+f"(d[86]), "+f"(d[87]), "+f"(d[88]), "+f"(d[89]), "+f"(d[90]), "+f"(d[91]), "+f"(d[92]), "+f"(d[93]), "+f"(d[94]), "+f"(d[95])
    : "l"(da), "l"(db), "r"(scale_d), "n"(TA), "n"(TB), "n"(SA));
}
template<int TA, int TB, int SA=1> __device__ __forceinline__ void wgmma_ss_n128(float (&d)[64], uint64_t da, uint64_t db, int scale_d) {
  asm volatile("{\n.reg .pred p;\nsetp.ne.b32 p, %66, 0;\n"
    "wgmma.mma_async.sync.aligned.m64n128k16.f32.bf16.bf16 {%0, %1, %2, %3, %4, %5, %6, %7, %8, %9, %10, %11, %12, %13, %14, %15, %16, %17, %18, %19, %20, %21, %22, %23, %24, %25, %26, %27, %28, %29, %30, %31, %32, %33, %34, %35, %36, %37, %38, %39, %40, %41, %42, %43, %44, %45, %46, %47, %48, %49, %50, %51, %52, %53, %54, %55, %56, %57, %58, %59, %60, %61, %62, %63}, %64, %65, p, %69, 1, %67, %68;\n}\n"
    : "+f"(d[0]), "+f"(d[1]), "+f"(d[2]), "+f"(d[3]), "+f"(d[4]), "+f"(d[5]), "+f"(d[6]), "+f"(d[7]), "+f"(d[8]), "+f"(d[9]), "+f"(d[10]), "+f"(d[11]), "+f"(d[12]), "+f"(d[13]), "+f"(d[14]), "+f"(d[15]), "+f"(d[16]), "+f"(d[17]), "+f"(d[18]), "+f"(d[19]), "+f"(d[20]), "+f"(d[21]), "+f"(d[22]), "+f"(d[23]), "+f"(d[24]), "+f"(d[25]), "+f"(d[26]), "+f"(d[27]), "+f"(d[28]), "+f"(d[29]), "+f"(d[30]), "+f"(d[31]), "+f"(d[32]), "+f"(d[33]), "+f"(d[34]), "+f"(d[35]), "+f"(d[36]), "+f"(d[37]), "+f"(d[38]), "+f"(d[39]), "+f"(d[40]), "+f"(d[41]), "+f"(d[42]), "+f"(d[43]), "+f"(d[44]), "+f"(d[45]), "+f"(d[46]), "+f"(d[47]), "+f"(d[48]), "+f"(d[49]), "+f"(d[50]), "+f"(d[51]), "+f"(d[52]), "+f"(d[53]), "+f"(d[54]), "+f"(d[55]), "+f"(d[56]), "+f"(d[57]), "+f"(d[58]), "+f"(d[59]), "+f"(d[60]), "+f"(d[61]), "+f"(d[62]), "+f"(d[63])
    : "l"(da), "l"(db), "r"(scale_d), "n"(TA), "n"(TB), "n"(SA));
}
template<int TA, int TB, int SA=1> __device__ __forceinline__ void wgmma_ss_n72(float (&d)[36], uint64_t da, uint64_t db, int scale_d) {
  asm volatile("{\n.reg .pred p;\nsetp.ne.b32 p, %38, 0;\n"
    "wgmma.mma_async.sync.aligned.m64n72k16.f32.bf16.bf16 {%0, %1, %2, %3, %4, %5, %6, %7, %8, %9, %10, %11, %12, %13, %14, %15, %16, %17, %18, %19, %20, %21, %22, %23, %24, %25, %26, %27, %28, %29, %30, %31, %32, %33, %34, %35}, %36, %37, p, %41, 1, %39, %40;\n}\n"
    : "+f"(d[0]), "+f"(d[1]), "+f"(d[2]), "+f"(d[3]), "+f"(d[4]), "+f"(d[5]), "+f"(d[6]), "+f"(d[7]), "+f"(d[8]), "+f"(d[9]), "+f"(d[10]), "+f"(d[11]), "+f"(d[12]), "+f"(d[13]), "+f"(d[14]), "+f"(d[15]), "+f"(d[16]), "+f"(d[17]), "+f"(d[18]), "+f"(d[19]), "+f"(d[20]), "+f"(d[21]), "+f"(d[22]), "+f"(d[23]), "+f"(d[24]), "+f"(d[25]), "+f"(d[26]), "+f"(d[27]), "+f"(d[28]), "+f"(d[29]), "+f"(d[30]), "+f"(d[31]), "+f"(d[32]), "+f"(d[33]), "+f"(d[34]), "+f"(d[35])
    : "l"(da), "l"(db), "r"(scale_d), "n"(TA), "n"(TB), "n"(SA));
}
template<int TB, int SA=1> __device__ __forceinline__ void wgmma_rs_n40(float (&d)[20], uint32_t a0, uint32_t a1, uint32_t a2, uint32_t a3, uint64_t db, int scale_d) {
  asm volatile("{\n.reg .pred p;\nsetp.ne.b32 p, %25, 0;\n"
    "wgmma.mma_async.sync.aligned.m64n40k16.f32.bf16.bf16 {%0, %1, %2, %3, %4, %5, %6, %7, %8, %9, %10, %11, %12, %13, %14, %15, %16, %17, %18, %19}, {%20, %21, %22, %23}, %24, p, %27, 1, %26;\n}\n"
    : "+f"(d[0]), "+f"(d[1]), "+f"(d[2]), "+f"(d[3]), "+f"(d[4]), "+f"(d[5]), "+f"(d[6]), "+f"(d[7]), "+f"(d[8]), "+f"(d[9]), "+f"(d[10]), "+f"(d[11]), "+f"(d[12]), "+f"(d[13]), "+f"(d[14]), "+f"(d[15]), "+f"(d[16]), "+f"(d[17]), "+f"(d[18]), "+f"(d[19])
    : "r"(a0), "r"(a1), "r"(a2), "r"(a3), "l"(db), "r"(scale_d), "n"(TB), "n"(SA));
}
template<int TB> __device__ __forceinline__ void wgmma_hrs_n64(uint32_t (&d)[16], uint32_t a0, uint32_t a1, uint32_t a2, uint32_t a3, uint64_t db, int scale_d) {
  asm volatile("{\n.reg .pred p;\nsetp.ne.b32 p, %21, 0;\n"
    "wgmma.mma_async.sync.aligned.m64n64k16.f16.f16.f16 {%0, %1, %2, %3, %4, %5, %6, %7, %8, %9, %10, %11, %12, %13, %14, %15}, {%16, %17, %18, %19}, %20, p, 1, 1, %22;\n}\n"
    : "+r"(d[0]), "+r"(d[1]), "+r"(d[2]), "+r"(d[3]), "+r"(d[4]), "+r"(d[5]), "+r"(d[6]), "+r"(d[7]), "+r"(d[8]), "+r"(d[9]), "+r"(d[10]), "+r"(d[11]), "+r"(d[12]), "+r"(d[13]), "+r"(d[14]), "+r"(d[15])
    : "r"(a0), "r"(a1), "r"(a2), "r"(a3), "l"(db), "r"(scale_d), "n"(TB));
}
template<int TB> __device__ __forceinline__ void wgmma_hrs_n32(uint32_t (&d)[8], uint32_t a0, uint32_t a1, uint32_t a2, uint32_t a3, uint64_t db, int scale_d) {
  asm volatile("{\n.reg .pred p;\nsetp.ne.b32 p, %13, 0;\n"
    "wgmma.mma_async.sync.aligned.m64n32k16.f16.f16.f16 {%0, %1, %2, %3, %4, %5, %6, %7}, {%8, %9, %10, %11}, %12, p, 1, 1, %14;\n}\n"
    : "+r"(d[0]), "+r"(d[1]), "+r"(d[2]), "+r"(d[3]), "+r"(d[4]), "+r"(d[5]), "+r"(d[6]), "+r"(d[7])
    : "r"(a0), "r"(a1), "r"(a2), "r"(a3), "l"(db), "r"(scale_d), "n"(TB));
}

__device__ __align__(128) const uint32_t c_thr[1536] = {
  0x33fb33ff,0xa49c9de4,0x33273352,0xaf2cae76,0x33e233f1,0xa96ca7bd,0x32c432f7,0xb045afdd,0x33b733cf,0xac3eaaf7,0x3250328c,0xb0eab099,
  0x3378339a,0xadbcacff,0x31cd3211,0xb182b137,0x33d033fb,0xaadea46a,0x299e2d17,0xb3e0b396,0x32fb337a,0xafd2adb1,0xa78b1f76,0xb3f2b3ff,
  0x318b3254,0xb1c5b0e5,0xae6bac32,0xb354b3b8,0x2f4230a3,0xb321b285,0xb133b040,0xb215b2c7,0x337c33f2,0xada5a759,0xb179afc8,0xb1d6b2fe,
  0x31463293,0xb204b08e,0xb394b2ba,0xad23b055,0x2b402f4e,0xb3cbb31e,0xb3e4b3f9,0x293ba533,0xac269c52,0xb3bab400,0xb258b357,0x30e02e5f,
  0x330133e5,0xafbda922,0xb3f3b3c9,0x2727ab59,0x2deb314a,0xb36fb200,0xb194b32f,0x31bc2f0a,0xacdb2084,0xb39fb3ff,0xa565aea4,0x33f93347,
  0xb2b6b0db,0xb05ab25c,0x30892c1a,0x329733bc,0x326033d4,0xb0d6aa94,0xb00ab29b,0x32e83084,0x20e82f64,0xb3feb318,0x2d8da597,0x338133f8,
  0xb1fcae48,0xb14fb35c,0x339031b8,0x2d3a3199,0xb3e6b3ae,0x2909ac7b,0x32d133f4,0xb030a6f5,0x319d33bf,0xb1b3ac02,0x2e3ca874,0x335e33ec,
  0xacc32b89,0xb3a3b3c6,0x33f83276,0x25c930b7,0xb3dcb1f8,0xaa01b154,0x30653335,0xb2b0aef4,0xb107b383,0x32392d81,0xafa6214d,0xb307b3fe,
  0x30bc33a5,0xb273acb7,0x33c5311b,0x2ba23229,0xb0cc94b6,0xb267b400,0x30153360,0xb2e1ae31,0xb385b3ab,0x2d76ac93,0xb166a691,0xb1e7b3f5,
  0x22deb06a,0x33fd32ac,0xb337b3da,0x2ee8aa19,0x2f853387,0xb310ad6a,0x322d33fe,0xb1162216,0xb2a9abd3,0xb06fb3c2,0xb07428a6,0xb2a5b3ea,
  0xb111b3e9,0x323128be,0xb30db3c3,0x2f90abba,0x31aa227a,0x31a633fd,0x2e25ad5e,0x33633389,0x2d6a3365,0xb387ae1a,0xa21631aa,0xb3feb1a6,
  0xb3c2af85,0xabd3b310,0xb3eab22d,0x28a6b116,0xa8beb2a9,0x33e9306f,0x2bbab074,0x33c332a5,0x33fd3111,0x227a3231,0x3389330d,0xad5e2f90,
  0x2a63333f,0xb3d7aec6,0xb2a2a1b1,0xb07ab3fe,0xb3f7b158,0x25fbb1f4,0xacb7b38b,0x33a52d52,0x2e0eb025,0x336832d8,0x340030bc,0x14b63273,
  0x323533c0,0xb10c2beb,0xac9330cc,0xb3abb267,0x23433316,0xb3fdaf6f,0xb38eb225,0x2d46b11f,0xb342b29e,0x2ebbb07f,0x31e3aa7c,0x316b33d6,
  0x3264a6c3,0x30d133f5,0x2c0233ac,0xb3bfac87,0x28f0336a,0xb3e7ae02,0xb3c6b19d,0x2b89b1b3,0xa59732e8,0xb3f8b00a,0xaccfb3ed,0x33a1285b,
  0xb1b8b381,0x3199ad8d,0x336c31df,0xadf73170,0x33f42d3a,0x26f53390,0xb30423a7,0xafb2b3fc,0xb05f3030,0xb2b3b2d1,0x29e8b27a,0x33dd30b2,
  0xab5932b6,0xb3c9b05a,0x30adb089,0x327e3297,0xaf0ab3f3,0x332fa727,0x240633b0,0xb3fcac6f,0x33473194,0xaea431bc,0xb174b359,0x31daae54,
  0xb3bca565,0xac1ab3f9,0x33ee2f59,0xa842331b,0xaddf3281,0xb371b0a8,0x34002b40,0x1c5233cb,0xa759b3ef,0x33f22829,0xb2fe2c26,0xafc8b3ba,
  0x308e337c,0xb2932da5,0x3055b179,0x32ba31d6,0xb31eb146,0x2f4eb204,0xa5333394,0xb3f9ad23,0xaff33249,0xb2f1b0f3,0x30e532fb,0xb2542fd2,
  0x2b28b373,0x33cc2dd4,0xb285b18b,0x30a3b1c5,0x246a33fa,0xb3fba500,0x33962f42,0xad173321,0xadb1b3d0,0x337aaade,0xb3ffa99e,0x1f76b3e0,
  0xb0ee320d,0xb24db13c,0xac4b3398,0xb3b5ad0b,0x304ab289,0x32c1309e,0x2985b3ce,0x33e12b0f,0xaf3732f4,0xb324afe8,0xa4ce33f0,0xb3faa7ef,
  0x2dc8b34f,0x33762e82,0x9de4b3ff,0x33ff1ead,0xb1c931cd,0xb186b182,0xb3762e82,0xadc8b34f,0x324db13c,0x30ee320d,0x33b5ad0b,0x2c4b3398,
  0xb2c1309e,0xb04ab289,0xb3e12b0f,0xa985b3ce,0x3324afe8,0x2f3732f4,0x33faa7ef,0x24ce33f0,0xb285318b,0xb0a3b1c5,0xb2c7ae6b,0x3040b354,
  0x3396af42,0x2d173321,0x31413133,0xb2093215,0xb3ff299e,0x9f76b3e0,0xae8db2bd,0x334cb050,0x33b8278b,0xac3233f2,0x281033b3,0xb3ef2c57,
  0xb31e3146,0xaf4eb204,0xa533b394,0x33f9ad23,0x3400ab40,0x9c5233cb,0xae5f33e4,0xb357a93b,0xb2feac26,0x2fc8b3ba,0x3245b258,0x30f830e0,
  0x30553179,0xb2ba31d6,0xb3df2e99,0xa9b6b34a,0xb39230fd,0xad2fb241,0x3200b301,0x314a2fbd,0x337f1b11,0xad993400,0xb3ff2deb,0xa084b36f,
  0xb005b129,0x32ebb21d,0x325c2cdb,0xb0db339f,0xa92233de,0xb3e529cf,0xab59b2b6,0x33c9b05a,0xb3dd30b2,0xa9e8b27a,0x33d4ab71,0xaa9433c8,
  0x32212c0e,0xb12433bd,0xaf64b0d6,0x3318b260,0x197fb345,0x3400aeaf,0xae4833fe,0xb35c20e8,0xb23d3332,0xb102aeff,0x33aeb14f,0x2c7b31fc,
  0xb3fe3065,0xa14db2b0,0x2ebb307f,0xb342329e,0x300f2fa6,0xb2e53307,0x30d1b3f5,0x326426c3,0x302ab400,0x32d517db,0xb3e72e02,0x28f0b36a,
  0xb3fd2f6f,0x2343b316,0x2d46311f,0xb38e3225,0xb3f53015,0x2691b2e1,0xaf9b33eb,0xb30a288d,0x2a193166,0xb3da31e7,0x33d7aec6,0xaa63333f,
  0x3313b337,0x2f7a2ee8,0xa5fbb1f4,0x33f7b158,0xb1a1a8d7,0x31afb3e8,0xb36832d8,0xae0eb025,0xb3c22f85,0x2bd3b310,0xb3ea322d,0xa8a6b116,
  0xa8be32a9,0xb3e9306f,0x2bba3074,0xb3c332a5,0x33fdb111,0xa27a3231,0x3389b30d,0x2d5e2f90,0xa216b1aa,0x33feb1a6,0xaed2ae25,0x333db363,
  0xb3652edd,0x2e1ab33a,0xb1aa227a,0x31a6b3fd,0xaf853387,0xb3102d6a,0xb22d33fe,0xb116a216,0x32a9abd3,0xb06f33c2,0x307428a6,0xb2a533ea,
  0x3111b3e9,0x3231a8be,0x330db3c3,0x2f902bba,0xb2e12e31,0x3015b360,0x288db1a1,0x33ebb1af,0xb1e733f5,0xb1662691,0xb33f2f9b,0x2ec6b30a,
  0x2ee82a19,0xb33733da,0xb15833d7,0xb1f42a63,0x33e8b313,0x28d72f7a,0x302525fb,0xb2d833f7,0xb2392d81,0x3107b383,0x3307b3fe,0x2fa6214d,
  0xb35e33ec,0xae3ca874,0x97dbb00f,0x3400b2e5,0xa5c930b7,0xb3f83276,0xb316302a,0x2f6fb2d5,0x32b0aef4,0xb0653335,0xb29e33fd,0xb07f2343,
  0xb1702ccf,0x31dfb3a1,0x3345b124,0xaeaf3221,0xb3fc336c,0xa3a7adf7,0x3332b400,0x2eff997f,0xb0b23304,0xb27a2fb2,0x2b71b102,0x33c8b23d,
  0x2c0e29e8,0xb3bd33dd,0xb0d62a94,0x3260b3d4,0xb0892c1a,0x3297b3bc,0x2aad2842,0xb3d333ee,0xb3b0327e,0x2c6fb0ad,0x3241b035,0xb0fd32ce,
  0xb35933fc,0xae542406,0x3400b392,0x1b112d2f,0xaf5931da,0xb31b3174,0x321db37f,0x3129ad99,0xaf152ac6,0x332cb3d2,0xb1463293,0xb204308e,
  0xb281312e,0x30a8b219,0xab402f4e,0xb3cb331e,0xb3ef3371,0x2829addf,0x2c269c52,0xb3ba3400,0xb37c33f2,0xada52759,0x3179afc8,0xb1d632fe,
  0xacf32953,0x339cb3e3,0xb3fa33cc,0x2500ab28,0xb0942f21,0x3290b32a,0xb3d033fb,0xaade246a,0xb249317d,0x30f3b1d2,0xb2fb337a,0xafd22db1,
  0xb37332f1,0x2dd4aff3,0xb18b3254,0xb1c530e5,0xa96c27bd,0x33e2b3f1,0xb0452fdd,0x32c4b2f7,0xac3e2af7,0x33b7b3cf,0xb0ea3099,0x3250b28c,
  0xadbc2cff,0x3378b39a,0xb1823137,0x31cdb211,0xaf2c2e76,0x3327b352,0xb20d31c9,0x313cb186,0x313c3186,0xb20db1c9,0x2d0b2dc8,0xb398b376,
  0x309e30ee,0xb289b24d,0x2b0f2c4b,0xb3ceb3b5,0x2fe8304a,0xb2f4b2c1,0x27ef2985,0xb3f0b3e1,0x2e822f37,0xb34fb324,0x1ead24ce,0xb3ffb3fa,
  0xb2bdb209,0xb050b141,0xb290b32a,0x30942f21,0xb3b3b34c,0xac57ae8d,0xb0f3b1d2,0x3249317d,0xb400b3ef,0x1d1ba810,0xadd4aff3,0x337332f1,
  0xb39cb3e3,0x2cf32953,0xa500ab28,0x33fa33cc,0xae99b0f8,0x334a3245,0x33ff33b2,0x201f2c63,0x2438a9b6,0x33fc33df,0x332c33d2,0xaf15aac6,
  0x303a2ce7,0x32cb339e,0x30a83219,0xb281b12e,0x32ee31c0,0x2ffe3190,0x28292ddf,0xb3efb371,0x33b0327e,0x2c6f30ad,0xb241b035,0xb0fdb2ce,
  0x335933fc,0xae54a406,0xb400b392,0x1b11ad2f,0x2f5931da,0xb31bb174,0xb21db37f,0x31292d99,0xaaad2842,0xb3d3b3ee,0xa9cfb005,0x33de32eb,
  0x285b305f,0xb3edb2b3,0x2c0ea9e8,0x33bd33dd,0xb170accf,0xb1dfb3a1,0x33453124,0x2eaf3221,0xb3fcb36c,0x23a7adf7,0x33323400,0xaeff997f,
  0xb0b2b304,0x327a2fb2,0x2b713102,0xb3c8b23d,0xb400b2e5,0x17dbb00f,0x2e023264,0xb36ab0d1,0xaf6fb2d5,0x3316302a,0xb11fa8f0,0xb225b3e7,
  0x307f2343,0x329e33fd,0xb3d6b38e,0x2a7cad46,0x33f53342,0xa6c32ebb,0xac87b1e3,0x33ac316b,0x28d7af7a,0x33e83313,0xb2d8b3f7,0x3025a5fb,
  0x33eb31af,0x288d31a1,0x2bebae0e,0x33c03368,0x2ec6330a,0xb33faf9b,0x33fe3235,0x21b1310c,0xb1f4aa63,0xb158b3d7,0x2d5232a2,0xb38bb07a,
  0x33a7333d,0xacab2ed2,0x33f63162,0x262d31eb,0xaa4b301a,0xb3d8b2de,0x2a32326b,0xb3d9b0c7,0xb3f6b26f,0x265fb0c1,0xb3a9b020,0xac9fb2db,
  0x0e48b15d,0x340031f0,0xae1ab33a,0x33652edd,0xaed22e25,0xb33db363,0xb1eb0e48,0xb162b400,0xb2deb3a7,0x301aacab,0xb0c7b3f6,0x326b262d,
  0x30c1aa4b,0x326f33d8,0x32db2a32,0x302033d9,0x31f033f6,0xb15d265f,0x2edd33a9,0xb33aac9f,0xb2acb385,0x306aad76,0x2a19b166,0x33da31e7,
  0x3229a2de,0x311b33fd,0x33133337,0xaf7a2ee8,0x2e3133c5,0xb360aba2,0xb1a128d7,0xb1afb3e8,0xb3f5b015,0xa691b2e1,0xaf9bb3eb,0x330a288d,
  0x3154acc3,0x31f833a3,0x2ef433f8,0xb335a5c9,0x2d8133dc,0xb383aa01,0xb3feb065,0x214db2b0,0xb3ecb107,0x2874b239,0x300fafa6,0x32e53307,
  0x30b7ae3c,0x3276335e,0x302a3400,0xb2d517db,0x312433bd,0xb2212c0e,0xb318b260,0x2f64b0d6,0xb400aeaf,0x997fb345,0x335c20e8,0x2e4833fe,
  0x3102aeff,0x323d3332,0xac7b31fc,0xb3aeb14f,0x2a9433c8,0xb3d4ab71,0xb084b3e6,0x329ba909,0xb2ce2aad,0xb035b3d3,0x33e529cf,0x292233de,
  0x2d2fb241,0x339230fd,0xb14a2fbd,0xb200b301,0x2d993400,0xb37f1b11,0x2084b36f,0x33ff2deb,0xb2ebb21d,0x3005b129,0x30db339f,0xb25c2cdb,
  0xae5fb3e4,0x3357a93b,0xb190303a,0xb1c0b2cb,0x32453258,0xb0f830e0,0x2c63b2ee,0x33b22ffe,0xb3dfae99,0x29b6b34a,0x2ac633ff,0xb3d2a01f,
  0x339ea438,0x2ce733fc,0xb12eb32c,0x3219af15,0x33b8a78b,0x2c3233f2,0x2810b3b3,0x33ef2c57,0xb2c72e6b,0xb040b354,0x29533400,0xb3e31d1b,
  0x3141b133,0x32093215,0xaf21b39c,0x332aacf3,0xae8d32bd,0xb34cb050,0x317d3290,0xb1d23094,0x27bd33fb,0xb3f1249c,0x2fdd3327,0xb2f72f2c,
  0xaaf7b3e2,0x33cfa96c,0xb099b2c4,0x328cb045,0x2cff33b7,0xb39a2c3e,0x31373250,0xb21130ea,0xae76b378,0x3352adbc,0xb1c9b1cd,0x3186b182,
  0xb3ff1ead,0x1de4b3ff,0xb352adbc,0x2e76b378,0x33f1249c,0xa7bd33fb,0x32f72f2c,0xafdd3327,0xb3cfa96c,0x2af7b3e2,0xb28cb045,0x3099b2c4,
  0x339a2c3e,0xacff33b7,0x321130ea,0xb1373250,0x2953b400,0x33e31d1b,0x33ccadd4,0x2b283373,0xaf21339c,0xb32aacf3,0xb3fb2500,0x246ab3fa,
  0x317db290,0x31d23094,0x337a2ade,0xadb133d0,0xb2f130f3,0xaff3b249,0xb254afd2,0x30e5b2fb,0x339e2438,0xace733fc,0xb12e332c,0xb219af15,
  0xb190b03a,0x31c0b2cb,0x3371b0a8,0x2ddf3281,0x2c6332ee,0xb3b22ffe,0xb3f22829,0x2759b3ef,0x2ac6b3ff,0x33d2a01f,0x32932da5,0xb08e337c,
  0xaf0a33f3,0xb32fa727,0x2406b3b0,0x33fcac6f,0x3347b194,0x2ea431bc,0xb1743359,0xb1daae54,0xb3bc2565,0x2c1ab3f9,0x33eeaf59,0x2842331b,
  0x30ad3089,0xb27e3297,0xb2ceaaad,0x3035b3d3,0xb29ba909,0x3084b3e6,0x305f3030,0xb2b332d1,0x259732e8,0xb3f8300a,0x2ccfb3ed,0x33a1a85b,
  0x31b8b381,0x31992d8d,0xb36c31df,0xadf7b170,0xb3f42d3a,0x26f5b390,0x330423a7,0xafb233fc,0x316bb3d6,0x31e32a7c,0xb3832a01,0x2d81b3dc,
  0xb3bf2c87,0x2c02b3ac,0x28743239,0xb3ec3107,0x2b8931b3,0xb3c6319d,0x3276b35e,0x30b72e3c,0x31f8b3a3,0x31542cc3,0xb33525c9,0x2ef4b3f8,
  0x310c2beb,0xb23533c0,0x33abb267,0x2c9330cc,0x307ab3fe,0x32a2a1b1,0xb06aad76,0x32acb385,0xb3a52d52,0x2cb7b38b,0xb11b33fd,0xb229a2de,
  0x94b63273,0xb40030bc,0x3360aba2,0xae3133c5,0xb2de33a7,0xb01aacab,0xb0c733f6,0xb26b262d,0x30c12a4b,0xb26f33d8,0x32dbaa32,0xb02033d9,
  0x31f0b3f6,0x315d265f,0x2eddb3a9,0x333aac9f,0xb1eb8e48,0x3162b400,0xb3872e1a,0x2d6ab365,0xae25ad5e,0x3363b389,0x8e48b15d,0x3400b1f0,
  0xb3a7333d,0xacabaed2,0xb3f63162,0x262db1eb,0x2a4b301a,0xb3d832de,0xaa32326b,0xb3d930c7,0x33f6b26f,0x265f30c1,0x33a9b020,0xac9f32db,
  0x33c0b368,0x2beb2e0e,0x30cc94b6,0xb2673400,0x21b1b10c,0x33feb235,0x3385b3ab,0x2d762c93,0xb38b307a,0x2d52b2a2,0xa2deb06a,0x33fdb2ac,
  0xb0bc33a5,0xb2732cb7,0xb3c5311b,0x2ba2b229,0x26c32ebb,0xb3f53342,0xb3ac316b,0x2c87b1e3,0x336ab0d1,0xae023264,0xb19d33bf,0xb1b32c02,
  0x3225b3e7,0x311fa8f0,0x2cc32b89,0xb3a333c6,0xaa7cad46,0x33d6b38e,0x33dcb1f8,0xaa013154,0xb3fe3318,0x20e8af64,0x3381b3f8,0x2d8d2597,
  0xb14f335c,0xb1fc2e48,0x2d3ab199,0x3390b1b8,0x29092c7b,0xb3e633ae,0xb03026f5,0x32d1b3f4,0x32e8b084,0xb00a329b,0xb3ed32b3,0x285bb05f,
  0x29cfb005,0x33deb2eb,0xb05a325c,0xb2b630db,0xafbd2922,0x3301b3e5,0x27272b59,0xb3f333c9,0xb36f3200,0x2debb14a,0x31bcaf0a,0xb194332f,
  0xb39f33ff,0xacdba084,0x33f9b347,0xa5652ea4,0x3394b2ba,0xad233055,0xa438a9b6,0x33fcb3df,0x33e4b3f9,0x293b2533,0xb03a2ce7,0x32cbb39e,
  0x3258b357,0x30e0ae5f,0xb2ee31c0,0x2ffeb190,0x2e99b0f8,0x334ab245,0xb3ff33b2,0x201fac63,0xaf4230a3,0xb3213285,0x3133b040,0xb21532c7,
  0xa99e2d17,0xb3e03396,0x32bdb209,0xb0503141,0x278b1f76,0xb3f233ff,0x33b3b34c,0xac572e8d,0x2e6bac32,0xb35433b8,0x3400b3ef,0x1d1b2810,
  0xb289324d,0x309eb0ee,0xb3ce33b5,0x2b0fac4b,0xb2f432c1,0x2fe8b04a,0xb3f033e1,0x27efa985,0xb34f3324,0x2e82af37,0xb3ff33fa,0x1eada4ce,
  0xb3983376,0x2d0badc8,0xb3fb33ff,0xa49c1de4,0x351c35f6,0xac93a617,0xb8a3b93c,0x308d2a16,0x32f43448,0xb160afa5,0xb6a4b7fe,0x353a3389,
  0x2fa53160,0xb448b2f4,0xb389b53a,0x37fe36a4,0x26172c93,0xb5f6b51c,0xaa16b08d,0x393c38a3,0x34c3358c,0xac47a5b2,0xb85fb8f3,0x304229b1,
  0x327e33fd,0xb106af26,0xb63cb785,0x34e7330f,0x2f263106,0xb3fdb27e,0xb30fb4e7,0x3785363c,0x25b22c47,0xb58cb4c3,0xa9b1b042,0x38f3385f,
  0x346a3523,0xabf6a54d,0xb81ab8a8,0x2fef294d,0x3209336b,0xb0acaea7,0xb5d4b70a,0x34933294,0x2ea730ac,0xb36bb209,0xb294b493,0x370a35d4,
  0x254d2bf6,0xb523b46a,0xa94dafef,0x38a8381a,0x341334bc,0xab5fa4e9,0xb7a6b85a,0x2f5928e8,0x319432da,0xb052ae28,0xb56ab68d,0x343e3219,
  0x2e283052,0xb2dab194,0xb219b43e,0x368d356a,0x24e92b5f,0xb4bcb413,0xa8e8af59,0x385a37a6,0x33783456,0xaac8a484,0xb715b80a,0x2ec32884,
  0x3120324a,0xaff2ada9,0xb4ffb60e,0x33d3319e,0x2da92ff2,0xb24ab120,0xb19eb3d3,0x360e34ff,0x24842ac8,0xb456b378,0xa884aec3,0x380a3715,
  0x32cd33e3,0xaa31a420,0xb682b76f,0x2e2d281f,0x30ac31bb,0xaf3fad2a,0xb493b58d,0x33283122,0x2d2a2f3f,0xb1bbb0ac,0xb122b328,0x358d3493,
  0x24202a31,0xb3e3b2cd,0xa81fae2d,0x376f3682,0x3223331c,0xa999a376,0xb5ebb6c6,0x2d972776,0x3039312d,0xae8dacac,0xb426b50b,0x327c30a6,
  0x2cac2e8d,0xb12db039,0xb0a6b27c,0x350b3426,0x23762999,0xb31cb223,0xa776ad97,0x36c635eb,0x317a3257,0xa902a2ad,0xb552b61a,0x2d0026ad,
  0x2f8c309f,0xaddcac2e,0xb371b487,0x31cf3029,0x2c2e2ddc,0xb09faf8c,0xb029b1cf,0x34873371,0x22ad2902,0xb257b17a,0xa6adad00,0x361a3552,
  0x30d23194,0xa86ba1e4,0xb4b7b56a,0x2c6a25e4,0x2ea73012,0xad2aab5f,0xb294b402,0x31222f59,0x2b5f2d2a,0xb012aea7,0xaf59b122,0x34023294,
  0x21e4286b,0xb194b0d2,0xa5e4ac6a,0x356a34b7,0x302c30d2,0xa7a9a11b,0xb41ab4b7,0x2ba7251b,0x2dc22f0c,0xac79aa63,0xb1b6b2f7,0x30742e5f,
  0x2a632c79,0xaf0cadc2,0xae5fb074,0x32f731b6,0x211b27a9,0xb0d2b02c,0xa51baba7,0x34b7341a,0x2f0c3012,0xa67ba052,0xb2f7b402,0x2a7a2452,
  0x2cde2df5,0xab91a967,0xb0d7b1e8,0x2f8b2d65,0x29672b91,0xadf5acde,0xad65af8b,0x31e830d7,0x2052267b,0xb012af0c,0xa452aa7a,0x340232f7,
  0x2dc22ea7,0xa54d9f12,0xb1b6b294,0x294d2311,0x2bf62cde,0xaa31a86b,0xafefb0d7,0x2e2d2c6a,0x286b2a31,0xacdeabf6,0xac6aae2d,0x30d72fef,
  0x1f12254d,0xaea7adc2,0xa311a94d,0x329431b6,0x2c792d2a,0xa4209d7f,0xb074b122,0x281f217f,0x2a312b91,0xa8d0a6e0,0xae2daf8b,0x2cce2ade,
  0x26e028d0,0xab91aa31,0xaadeacce,0x2f8b2e2d,0x1d7f2420,0xad2aac79,0xa17fa81f,0x31223074,0x2a632b5f,0xa1e49bdb,0xae5faf59,0x25e41fdb,
  0x286b2967,0xa6e0a4e9,0xac6aad65,0x2ade28e8,0x24e926e0,0xa967a86b,0xa8e8aade,0x2d652c6a,0x1bdb21e4,0xab5faa63,0x9fdba5e4,0x2f592e5f,
  0x27a9286b,0x9f1298b6,0xaba7ac6a,0x23111cb6,0x254d267b,0xa420a1e4,0xa94daa7a,0x281f25e4,0x21e42420,0xa67ba54d,0xa5e4a81f,0x2a7a294d,
  0x18b61f12,0xa86ba7a9,0x9cb6a311,0x2c6a2ba7,0x211b21e4,0x98b69248,0xa51ba5e4,0x1cb61648,0x1f122052,0x9d7f9bdb,0xa311a452,0x217f1fdb,
  0x1bdb1d7f,0xa0529f12,0x9fdba17f,0x24522311,0x124818b6,0xa1e4a11b,0x96489cb6,0x25e4251b,0xa11ba1e4,0x18b61248,0x251b25e4,0x9cb69648,
  0x9f12a052,0x1d7f1bdb,0x23112452,0xa17f9fdb,0x9bdb9d7f,0x20521f12,0x1fdb217f,0xa452a311,0x924898b6,0x21e4211b,0x16481cb6,0xa5e4a51b,
  0xa7a9a86b,0x1f1218b6,0x2ba72c6a,0xa3119cb6,0xa54da67b,0x242021e4,0x294d2a7a,0xa81fa5e4,0xa1e4a420,0x267b254d,0x25e4281f,0xaa7aa94d,
  0x98b69f12,0x286b27a9,0x1cb62311,0xac6aaba7,0xaa63ab5f,0x21e41bdb,0x2e5f2f59,0xa5e49fdb,0xa86ba967,0x26e024e9,0x2c6a2d65,0xaadea8e8,
  0xa4e9a6e0,0x2967286b,0x28e82ade,0xad65ac6a,0x9bdba1e4,0x2b5f2a63,0x1fdb25e4,0xaf59ae5f,0xac79ad2a,0x24201d7f,0x30743122,0xa81fa17f,
  0xaa31ab91,0x28d026e0,0x2e2d2f8b,0xacceaade,0xa6e0a8d0,0x2b912a31,0x2ade2cce,0xaf8bae2d,0x9d7fa420,0x2d2a2c79,0x217f281f,0xb122b074,
  0xadc2aea7,0x254d1f12,0x31b63294,0xa94da311,0xabf6acde,0x2a31286b,0x2fef30d7,0xae2dac6a,0xa86baa31,0x2cde2bf6,0x2c6a2e2d,0xb0d7afef,
  0x9f12a54d,0x2ea72dc2,0x2311294d,0xb294b1b6,0xaf0cb012,0x267b2052,0x32f73402,0xaa7aa452,0xacdeadf5,0x2b912967,0x30d731e8,0xaf8bad65,
  0xa967ab91,0x2df52cde,0x2d652f8b,0xb1e8b0d7,0xa052a67b,0x30122f0c,0x24522a7a,0xb402b2f7,0xb02cb0d2,0x27a9211b,0x341a34b7,0xaba7a51b,
  0xadc2af0c,0x2c792a63,0x31b632f7,0xb074ae5f,0xaa63ac79,0x2f0c2dc2,0x2e5f3074,0xb2f7b1b6,0xa11ba7a9,0x30d2302c,0x251b2ba7,0xb4b7b41a,
  0xb0d2b194,0x286b21e4,0x34b7356a,0xac6aa5e4,0xaea7b012,0x2d2a2b5f,0x32943402,0xb122af59,0xab5fad2a,0x30122ea7,0x2f593122,0xb402b294,
  0xa1e4a86b,0x319430d2,0x25e42c6a,0xb56ab4b7,0xb17ab257,0x290222ad,0x3552361a,0xad00a6ad,0xaf8cb09f,0x2ddc2c2e,0x33713487,0xb1cfb029,
  0xac2eaddc,0x309f2f8c,0x302931cf,0xb487b371,0xa2ada902,0x3257317a,0x26ad2d00,0xb61ab552,0xb223b31c,0x29992376,0x35eb36c6,0xad97a776,
  0xb039b12d,0x2e8d2cac,0x3426350b,0xb27cb0a6,0xacacae8d,0x312d3039,0x30a6327c,0xb50bb426,0xa376a999,0x331c3223,0x27762d97,0xb6c6b5eb,
  0xb2cdb3e3,0x2a312420,0x3682376f,0xae2da81f,0xb0acb1bb,0x2f3f2d2a,0x3493358d,0xb328b122,0xad2aaf3f,0x31bb30ac,0x31223328,0xb58db493,
  0xa420aa31,0x33e332cd,0x281f2e2d,0xb76fb682,0xb378b456,0x2ac82484,0x3715380a,0xaec3a884,0xb120b24a,0x2ff22da9,0x34ff360e,0xb3d3b19e,
  0xada9aff2,0x324a3120,0x319e33d3,0xb60eb4ff,0xa484aac8,0x34563378,0x28842ec3,0xb80ab715,0xb413b4bc,0x2b5f24e9,0x37a6385a,0xaf59a8e8,
  0xb194b2da,0x30522e28,0x356a368d,0xb43eb219,0xae28b052,0x32da3194,0x3219343e,0xb68db56a,0xa4e9ab5f,0x34bc3413,0x28e82f59,0xb85ab7a6,
  0xb46ab523,0x2bf6254d,0x381a38a8,0xafefa94d,0xb209b36b,0x30ac2ea7,0x35d4370a,0xb493b294,0xaea7b0ac,0x336b3209,0x32943493,0xb70ab5d4,
  0xa54dabf6,0x3523346a,0x294d2fef,0xb8a8b81a,0xb4c3b58c,0x2c4725b2,0x385f38f3,0xb042a9b1,0xb27eb3fd,0x31062f26,0x363c3785,0xb4e7b30f,
  0xaf26b106,0x33fd327e,0x330f34e7,0xb785b63c,0xa5b2ac47,0x358c34c3,0x29b13042,0xb8f3b85f,0xb51cb5f6,0x2c932617,0x38a3393c,0xb08daa16,
  0xb2f4b448,0x31602fa5,0x36a437fe,0xb53ab389,0xafa5b160,0x344832f4,0x3389353a,0xb7feb6a4,0xa617ac93,0x35f6351c,0x2a16308d,0xb93cb8a3,
};
__device__ __align__(128) const uint32_t c_img[2560] = {
  0x326d31ed,0x333b32dd,0x33c33388,0x33fe33ea,0x33c331ed,0x31ed33c3,0xa8b22d64,0xb33bb0c4,0x33ea31ed,0xad64301d,0xb2ddb388,0x315fa8b2,
  0x32dd31ed,0xb3feabc6,0x326dad64,0xad64326d,0x30c431ed,0xaed7b2dd,0x2bc63388,0xa248b3ea,0x2bc631ed,0x315fb3c3,0xb3ea2d64,0x2ed730c4,
  0xa8b231ed,0x3388b01d,0x301db388,0xb1ed28b2,0xb01d31ed,0x22482bc6,0x30c4ad64,0x3388b26d,0x33ea33fe,0x338833c3,0x32dd333b,0x31ed326d,
  0xb2ddb3fe,0xa248b01d,0x326d2ed7,0x338833ea,0x30c433fe,0xb33babc6,0xabc6b33b,0x33fe30c4,0xabc6b3fe,0x31ed32dd,0xb3eaaed7,0x333ba8b2,
  0xa8b233fe,0x2d64b3c3,0xb01d333b,0x315fb26d,0x301db3fe,0xb3fe301d,0x30c42ed7,0x2d64b3ea,0xb26d33fe,0x2ed72bc6,0x33c3b33b,0xa248b0c4,
  0x33c3b3fe,0x315fb2dd,0x28b2aed7,0xaed728b2,0xb0c4b15f,0xaed7b01d,0xabc6ad64,0xa248a8b2,0xabc6b15f,0x315f2bc6,0x33ea3388,0x2ed7326d,
  0x28b2b15f,0x338832dd,0xb01d2d64,0xb1edb3ea,0x301db15f,0x224833c3,0xb0c4b388,0x338830c4,0x326db15f,0xb33b301d,0x33c3ad64,0xb3fe28b2,
  0x33c3b15f,0xb1edabc6,0xa8b23388,0x333bb26d,0x33eab15f,0x2d64b2dd,0xb2dd2d64,0xb15f33ea,0x32ddb15f,0x33feb3c3,0x326db388,0x2d64b0c4,
  0x28b22248,0x2d642bc6,0x301d2ed7,0x315f30c4,0xb01da248,0xb3feb2dd,0xb0c4b33b,0x2d64a8b2,0x326d2248,0x2ed733c3,0xb3c3aed7,0xa248b26d,
  0xb3c3a248,0x315fb01d,0xa8b2333b,0xaed7b3ea,0x33ea2248,0xb388abc6,0x32dd2ed7,0xb1edb0c4,0xb2dda248,0x224832dd,0x326db33b,0xb38828b2,
  0x30c42248,0x333bb3c3,0xabc6aed7,0xb3fe326d,0xabc6a248,0xb1ed301d,0xb3ea333b,0xb33b33ea,0xb26d31ed,0xb33b32dd,0xb3c33388,0xb3fe33ea,
  0xb3c331ed,0xb1ed33c3,0x28b22d64,0x333bb0c4,0xb3ea31ed,0x2d64301d,0x32ddb388,0xb15fa8b2,0xb2dd31ed,0x33feabc6,0xb26dad64,0x2d64326d,
  0xb0c431ed,0x2ed7b2dd,0xabc63388,0x2248b3ea,0xabc631ed,0xb15fb3c3,0x33ea2d64,0xaed730c4,0x28b231ed,0xb388b01d,0xb01db388,0x31ed28b2,
  0x301d31ed,0xa2482bc6,0xb0c4ad64,0xb388b26d,0xb3ea33fe,0xb38833c3,0xb2dd333b,0xb1ed326d,0x32ddb3fe,0x2248b01d,0xb26d2ed7,0xb38833ea,
  0xb0c433fe,0x333babc6,0x2bc6b33b,0xb3fe30c4,0x2bc6b3fe,0xb1ed32dd,0x33eaaed7,0xb33ba8b2,0x28b233fe,0xad64b3c3,0x301d333b,0xb15fb26d,
  0xb01db3fe,0x33fe301d,0xb0c42ed7,0xad64b3ea,0x326d33fe,0xaed72bc6,0xb3c3b33b,0x2248b0c4,0xb3c3b3fe,0xb15fb2dd,0xa8b2aed7,0x2ed728b2,
  0x30c4b15f,0x2ed7b01d,0x2bc6ad64,0x2248a8b2,0x2bc6b15f,0xb15f2bc6,0xb3ea3388,0xaed7326d,0xa8b2b15f,0xb38832dd,0x301d2d64,0x31edb3ea,
  0xb01db15f,0xa24833c3,0x30c4b388,0xb38830c4,0xb26db15f,0x333b301d,0xb3c3ad64,0x33fe28b2,0xb3c3b15f,0x31edabc6,0x28b23388,0xb33bb26d,
  0xb3eab15f,0xad64b2dd,0x32dd2d64,0x315f33ea,0xb2ddb15f,0xb3feb3c3,0xb26db388,0xad64b0c4,0xa8b22248,0xad642bc6,0xb01d2ed7,0xb15f30c4,
  0x301da248,0x33feb2dd,0x30c4b33b,0xad64a8b2,0xb26d2248,0xaed733c3,0x33c3aed7,0x2248b26d,0x33c3a248,0xb15fb01d,0x28b2333b,0x2ed7b3ea,
  0xb3ea2248,0x3388abc6,0xb2dd2ed7,0x31edb0c4,0x32dda248,0xa24832dd,0xb26db33b,0x338828b2,0xb0c42248,0xb33bb3c3,0x2bc6aed7,0x33fe326d,
  0x2bc6a248,0x31ed301d,0x33ea333b,0x333b33ea,0x30c4315f,0x2ed7301d,0x2bc62d64,0x224828b2,0x2bc6315f,0xb15fabc6,0xb3eab388,0xaed7b26d,
  0xa8b2315f,0xb388b2dd,0x301dad64,0x31ed33ea,0xb01d315f,0xa248b3c3,0x30c43388,0xb388b0c4,0xb26d315f,0x333bb01d,0xb3c32d64,0x33fea8b2,
  0xb3c3315f,0x31ed2bc6,0x28b2b388,0xb33b326d,0xb3ea315f,0xad6432dd,0x32ddad64,0x315fb3ea,0xb2dd315f,0xb3fe33c3,0xb26d3388,0xad6430c4,
  0xa8b2a248,0xad64abc6,0xb01daed7,0xb15fb0c4,0x301d2248,0x33fe32dd,0x30c4333b,0xad6428b2,0xb26da248,0xaed7b3c3,0x33c32ed7,0x2248326d,
  0x33c32248,0xb15f301d,0x28b2b33b,0x2ed733ea,0xb3eaa248,0x33882bc6,0xb2ddaed7,0x31ed30c4,0x32dd2248,0xa248b2dd,0xb26d333b,0x3388a8b2,
  0xb0c4a248,0xb33b33c3,0x2bc62ed7,0x33feb26d,0x2bc62248,0x31edb01d,0x33eab33b,0x333bb3ea,0x326d31ed,0x333b32dd,0x33c33388,0x33fe33ea,
  0x33c331ed,0x31ed33c3,0xa8b22d64,0xb33bb0c4,0x33ea31ed,0xad64301d,0xb2ddb388,0x315fa8b2,0x32dd31ed,0xb3feabc6,0x326dad64,0xad64326d,
  0x30c431ed,0xaed7b2dd,0x2bc63388,0xa248b3ea,0x2bc631ed,0x315fb3c3,0xb3ea2d64,0x2ed730c4,0xa8b231ed,0x3388b01d,0x301db388,0xb1ed28b2,
  0xb01d31ed,0x22482bc6,0x30c4ad64,0x3388b26d,0x33ea33fe,0x338833c3,0x32dd333b,0x31ed326d,0xb2ddb3fe,0xa248b01d,0x326d2ed7,0x338833ea,
  0x30c433fe,0xb33babc6,0xabc6b33b,0x33fe30c4,0xabc6b3fe,0x31ed32dd,0xb3eaaed7,0x333ba8b2,0xa8b233fe,0x2d64b3c3,0xb01d333b,0x315fb26d,
  0x301db3fe,0xb3fe301d,0x30c42ed7,0x2d64b3ea,0xb26d33fe,0x2ed72bc6,0x33c3b33b,0xa248b0c4,0x33c3b3fe,0x315fb2dd,0x28b2aed7,0xaed728b2,
  0xb0c4315f,0xaed7301d,0xabc62d64,0xa24828b2,0xabc6315f,0x315fabc6,0x33eab388,0x2ed7b26d,0x28b2315f,0x3388b2dd,0xb01dad64,0xb1ed33ea,
  0x301d315f,0x2248b3c3,0xb0c43388,0x3388b0c4,0x326d315f,0xb33bb01d,0x33c32d64,0xb3fea8b2,0x33c3315f,0xb1ed2bc6,0xa8b2b388,0x333b326d,
  0x33ea315f,0x2d6432dd,0xb2ddad64,0xb15fb3ea,0x32dd315f,0x33fe33c3,0x326d3388,0x2d6430c4,0x28b2a248,0x2d64abc6,0x301daed7,0x315fb0c4,
  0xb01d2248,0xb3fe32dd,0xb0c4333b,0x2d6428b2,0x326da248,0x2ed7b3c3,0xb3c32ed7,0xa248326d,0xb3c32248,0x315f301d,0xa8b2b33b,0xaed733ea,
  0x33eaa248,0xb3882bc6,0x32ddaed7,0xb1ed30c4,0xb2dd2248,0x2248b2dd,0x326d333b,0xb388a8b2,0x30c4a248,0x333b33c3,0xabc62ed7,0xb3feb26d,
  0xabc62248,0xb1edb01d,0xb3eab33b,0xb33bb3ea,0xb26d31ed,0xb33b32dd,0xb3c33388,0xb3fe33ea,0xb3c331ed,0xb1ed33c3,0x28b22d64,0x333bb0c4,
  0xb3ea31ed,0x2d64301d,0x32ddb388,0xb15fa8b2,0xb2dd31ed,0x33feabc6,0xb26dad64,0x2d64326d,0xb0c431ed,0x2ed7b2dd,0xabc63388,0x2248b3ea,
  0xabc631ed,0xb15fb3c3,0x33ea2d64,0xaed730c4,0x28b231ed,0xb388b01d,0xb01db388,0x31ed28b2,0x301d31ed,0xa2482bc6,0xb0c4ad64,0xb388b26d,
  0xb3ea33fe,0xb38833c3,0xb2dd333b,0xb1ed326d,0x32ddb3fe,0x2248b01d,0xb26d2ed7,0xb38833ea,0xb0c433fe,0x333babc6,0x2bc6b33b,0xb3fe30c4,
  0x2bc6b3fe,0xb1ed32dd,0x33eaaed7,0xb33ba8b2,0x28b233fe,0xad64b3c3,0x301d333b,0xb15fb26d,0xb01db3fe,0x33fe301d,0xb0c42ed7,0xad64b3ea,
  0x326d33fe,0xaed72bc6,0xb3c3b33b,0x2248b0c4,0xb3c3b3fe,0xb15fb2dd,0xa8b2aed7,0x2ed728b2,0x29ed29ed,0x29ed29ed,0x29ed29ed,0x29ed29ed,
  0x2bc32a6d,0x2add2bea,0x23c628c4,0xa81da0b2,0x2bc32add,0xa3c6281d,0xabc3aadd,0x23c6a81d,0x29ed2b3b,0xabfea564,0x295fa6d7,0x1a482b88,
  0x25642b88,0xa564ab88,0x25642b88,0xa564ab88,0xa0b22bc3,0x2a6daadd,0xabea23c6,0x28c4281d,0xa8c42bea,0x2a6da0b2,0x28c4abea,0xaa6d20b2,
  0xab3b2bfe,0xa564295f,0x26d79a48,0x2b88a9ed,0x29ed29ed,0x29ed29ed,0x29ed29ed,0x29ed29ed,0xabc3aa6d,0xaaddabea,0xa3c6a8c4,0x281d20b2,
  0x2bc32add,0xa3c6281d,0xabc3aadd,0x23c6a81d,0xa9edab3b,0x2bfe2564,0xa95f26d7,0x9a48ab88,0x25642b88,0xa564ab88,0x25642b88,0xa564ab88,
  0x20b2abc3,0xaa6d2add,0x2beaa3c6,0xa8c4a81d,0xa8c42bea,0x2a6da0b2,0x28c4abea,0xaa6d20b2,0x2b3babfe,0x2564a95f,0xa6d71a48,0xab8829ed,
  0x295f295f,0x295f295f,0x295f295f,0x295f295f,0x23c628c4,0xa81da0b2,0xabc3aa6d,0xaaddabea,0xa3c6281d,0xabc3aadd,0x23c6a81d,0x2bc32add,
  0xa95f26d7,0x9a48ab88,0x29ed2b3b,0xabfea564,0xab882564,0x2b88a564,0xab882564,0x2b88a564,0xabea23c6,0x28c4281d,0x20b2abc3,0xaa6d2add,
  0xaa6d20b2,0xa8c42bea,0x2a6da0b2,0x28c4abea,0xa6d71a48,0xab8829ed,0xab3b2bfe,0xa564295f,0x295f295f,0x295f295f,0x295f295f,0x295f295f,
  0xa3c6a8c4,0x281d20b2,0x2bc32a6d,0x2add2bea,0xa3c6281d,0xabc3aadd,0x23c6a81d,0x2bc32add,0x295fa6d7,0x1a482b88,0xa9edab3b,0x2bfe2564,
  0xab882564,0x2b88a564,0xab882564,0x2b88a564,0x2beaa3c6,0xa8c4a81d,0xa0b22bc3,0x2a6daadd,0xaa6d20b2,0xa8c42bea,0x2a6da0b2,0x28c4abea,
  0x26d79a48,0x2b88a9ed,0x2b3babfe,0x2564a95f,0xabfe2bfe,0xabfe2bfe,0xabfe2bfe,0xabfe2bfe,0xaadd2bea,0xa3c628c4,0x281da0b2,0x2bc3aa6d,
  0xa81d2bc3,0x2adda3c6,0x281dabc3,0xaadd23c6,0x9a482b88,0x29edab3b,0xabfe2564,0x295f26d7,0x26d72b3b,0xa6d7ab3b,0x26d72b3b,0xa6d7ab3b,
  0x2a6d2add,0xabeaa3c6,0x28c4a81d,0x20b22bc3,0x2bea2a6d,0xa0b228c4,0xabeaaa6d,0x20b2a8c4,0x2b8829ed,0x2b3b2bfe,0x2564295f,0xa6d79a48,
  0xabfe2bfe,0xabfe2bfe,0xabfe2bfe,0xabfe2bfe,0x2addabea,0x23c6a8c4,0xa81d20b2,0xabc32a6d,0xa81d2bc3,0x2adda3c6,0x281dabc3,0xaadd23c6,
  0x1a48ab88,0xa9ed2b3b,0x2bfea564,0xa95fa6d7,0x26d72b3b,0xa6d7ab3b,0x26d72b3b,0xa6d7ab3b,0xaa6daadd,0x2bea23c6,0xa8c4281d,0xa0b2abc3,
  0x2bea2a6d,0xa0b228c4,0xabeaaa6d,0x20b2a8c4,0xab88a9ed,0xab3babfe,0xa564a95f,0x26d71a48,0x1a489a48,0x1a489a48,0x1a489a48,0x1a489a48,
  0x281da0b2,0x2bc3aa6d,0x2addabea,0x23c6a8c4,0x2adda3c6,0x281dabc3,0xaadd23c6,0xa81d2bc3,0x2bfea564,0xa95fa6d7,0x9a482b88,0x29edab3b,
  0x2b3ba6d7,0xab3b26d7,0x2b3ba6d7,0xab3b26d7,0x28c4a81d,0x20b22bc3,0xaa6daadd,0x2bea23c6,0x20b2a8c4,0x2bea2a6d,0xa0b228c4,0xabeaaa6d,
  0xa564a95f,0x26d71a48,0x2b8829ed,0x2b3b2bfe,0x1a489a48,0x1a489a48,0x1a489a48,0x1a489a48,0xa81d20b2,0xabc32a6d,0xaadd2bea,0xa3c628c4,
  0x2adda3c6,0x281dabc3,0xaadd23c6,0xa81d2bc3,0xabfe2564,0x295f26d7,0x1a48ab88,0xa9ed2b3b,0x2b3ba6d7,0xab3b26d7,0x2b3ba6d7,0xab3b26d7,
  0xa8c4281d,0xa0b2abc3,0x2a6d2add,0xabeaa3c6,0x20b2a8c4,0x2bea2a6d,0xa0b228c4,0xabeaaa6d,0x2564295f,0xa6d79a48,0xab88a9ed,0xab3babfe,
  0xa95fa95f,0xa95fa95f,0xa95fa95f,0xa95fa95f,0xa3c6a8c4,0x281d20b2,0x2bc32a6d,0x2add2bea,0x23c6a81d,0x2bc32add,0xa3c6281d,0xabc3aadd,
  0x295fa6d7,0x1a482b88,0xa9edab3b,0x2bfe2564,0x2b88a564,0xab882564,0x2b88a564,0xab882564,0x2beaa3c6,0xa8c4a81d,0xa0b22bc3,0x2a6daadd,
  0x2a6da0b2,0x28c4abea,0xaa6d20b2,0xa8c42bea,0x26d79a48,0x2b88a9ed,0x2b3babfe,0x2564a95f,0xa95fa95f,0xa95fa95f,0xa95fa95f,0xa95fa95f,
  0x23c628c4,0xa81da0b2,0xabc3aa6d,0xaaddabea,0x23c6a81d,0x2bc32add,0xa3c6281d,0xabc3aadd,0xa95f26d7,0x9a48ab88,0x29ed2b3b,0xabfea564,
  0x2b88a564,0xab882564,0x2b88a564,0xab882564,0xabea23c6,0x28c4281d,0x20b2abc3,0xaa6d2add,0x2a6da0b2,0x28c4abea,0xaa6d20b2,0xa8c42bea,
  0xa6d71a48,0xab8829ed,0xab3b2bfe,0xa564295f,0x29ed29ed,0x29ed29ed,0x29ed29ed,0x29ed29ed,0x2bc32a6d,0x2add2bea,0x23c628c4,0xa81da0b2,
  0x2bc32add,0xa3c6281d,0xabc3aadd,0x23c6a81d,0x29ed2b3b,0xabfea564,0x295fa6d7,0x1a482b88,0x25642b88,0xa564ab88,0x25642b88,0xa564ab88,
  0xa0b22bc3,0x2a6daadd,0xabea23c6,0x28c4281d,0xa8c42bea,0x2a6da0b2,0x28c4abea,0xaa6d20b2,0xab3b2bfe,0xa564295f,0x26d79a48,0x2b88a9ed,
  0x29ed29ed,0x29ed29ed,0x29ed29ed,0x29ed29ed,0xabc3aa6d,0xaaddabea,0xa3c6a8c4,0x281d20b2,0x2bc32add,0xa3c6281d,0xabc3aadd,0x23c6a81d,
  0xa9edab3b,0x2bfe2564,0xa95f26d7,0x9a48ab88,0x25642b88,0xa564ab88,0x25642b88,0xa564ab88,0x20b2abc3,0xaa6d2add,0x2beaa3c6,0xa8c4a81d,
  0xa8c42bea,0x2a6da0b2,0x28c4abea,0xaa6d20b2,0x2b3babfe,0x2564a95f,0xa6d71a48,0xab8829ed,0x9a481a48,0x9a481a48,0x9a481a48,0x9a481a48,
  0xa81d20b2,0xabc32a6d,0xaadd2bea,0xa3c628c4,0xaadd23c6,0xa81d2bc3,0x2adda3c6,0x281dabc3,0xabfe2564,0x295f26d7,0x1a48ab88,0xa9ed2b3b,
  0xab3b26d7,0x2b3ba6d7,0xab3b26d7,0x2b3ba6d7,0xa8c4281d,0xa0b2abc3,0x2a6d2add,0xabeaa3c6,0xa0b228c4,0xabeaaa6d,0x20b2a8c4,0x2bea2a6d,
  0x2564295f,0xa6d79a48,0xab88a9ed,0xab3babfe,0x9a481a48,0x9a481a48,0x9a481a48,0x9a481a48,0x281da0b2,0x2bc3aa6d,0x2addabea,0x23c6a8c4,
  0xaadd23c6,0xa81d2bc3,0x2adda3c6,0x281dabc3,0x2bfea564,0xa95fa6d7,0x9a482b88,0x29edab3b,0xab3b26d7,0x2b3ba6d7,0xab3b26d7,0x2b3ba6d7,
  0x28c4a81d,0x20b22bc3,0xaa6daadd,0x2bea23c6,0xa0b228c4,0xabeaaa6d,0x20b2a8c4,0x2bea2a6d,0xa564a95f,0x26d71a48,0x2b8829ed,0x2b3b2bfe,
  0xabfe2bfe,0xabfe2bfe,0xabfe2bfe,0xabfe2bfe,0xaadd2bea,0xa3c628c4,0x281da0b2,0x2bc3aa6d,0xa81d2bc3,0x2adda3c6,0x281dabc3,0xaadd23c6,
  0x9a482b88,0x29edab3b,0xabfe2564,0x295f26d7,0x26d72b3b,0xa6d7ab3b,0x26d72b3b,0xa6d7ab3b,0x2a6d2add,0xabeaa3c6,0x28c4a81d,0x20b22bc3,
  0x2bea2a6d,0xa0b228c4,0xabeaaa6d,0x20b2a8c4,0x2b8829ed,0x2b3b2bfe,0x2564295f,0xa6d79a48,0xabfe2bfe,0xabfe2bfe,0xabfe2bfe,0xabfe2bfe,
  0x2addabea,0x23c6a8c4,0xa81d20b2,0xabc32a6d,0xa81d2bc3,0x2adda3c6,0x281dabc3,0xaadd23c6,0x1a48ab88,0xa9ed2b3b,0x2bfea564,0xa95fa6d7,
  0x26d72b3b,0xa6d7ab3b,0x26d72b3b,0xa6d7ab3b,0xaa6daadd,0x2bea23c6,0xa8c4281d,0xa0b2abc3,0x2bea2a6d,0xa0b228c4,0xabeaaa6d,0x20b2a8c4,
  0xab88a9ed,0xab3babfe,0xa564a95f,0x26d71a48,0x3bfb3bff,0x3be53bf2,0x3bbf3bd4,0x3b873ba5,0x3bd03bfb,0x3b013b7c,0x399d3a60,0x378538bc,
  0x35173b52,0xbbc9b7c8,0xb074ba9b,0x3bfe391b,0x319e3b27,0xbbf3b979,0x363cb80a,0x3a2d3bc5,0xba093986,0x3a7eb8f8,0xbae5385f,0x3b3db77a,
  0xbabd393c,0x3bb0b699,0xbc00305b,0x3ba730d7,0xbb2a35c8,0xb8353bb2,0x3a64b1e8,0x3962bbf7,0xba90350b,0xba413bff,0x3602340e,0x3bf6bad8,
  0xac6aa5e4,0xb122af59,0xb402b294,0xb56ab4b7,0xb2deac9c,0xb7bdb5a5,0xb9b3b8d6,0xbb10ba73,0xbb96b676,0xb359bafe,0x3bec3884,0x2a163a29,
  0xbbe0b72c,0x2f27b9d6,0x3b5e3ae8,0xb91633a2,0xb941b9c9,0x38ad3a45,0xb80fbab3,0x36d23b13,0xb850ba0d,0x346f3b4a,0x1fdbbbed,0xb4ab3be8,
  0x3721bb76,0xbace3463,0xb8d13bdd,0x39ebadfb,0x3894bb98,0xb8fd281f,0xbb6a3bbd,0x2e2d3825,0x3b3f3b65,0x3ae83b16,0x3a813ab6,0x3a0d3a49,
  0x3263356a,0xad972b43,0xb5dfb359,0xb8eeb7f3,0xa9b139aa,0xbbedba25,0x3340b889,0x3b983afb,0xbaa2aa16,0xb4cfbb8e,0x3c0038ad,0xb44b38e5,
  0xbb853625,0x3bbdb4c3,0xbbe432ad,0x3bfbaf8b,0xbaacb6d2,0x39243954,0xb65fbace,0x2fbd3bb8,0xb9661648,0xba603bf8,0x383a31cf,0x3b27bbb3,
  0x3219b9eb,0xbb1836f4,0xb9903be5,0x37dd3010,0xb6c6b61a,0xb80ab76f,0xb8a8b85a,0xb93cb8f3,0xbbd7bb87,0xbbf8bbfd,0xbb71bbc9,0xba4dbaf1,
  0xbbfeb9a6,0x305bb91f,0x3bcb3a97,0xb50b37d2,0xb87abbfe,0x3ba13546,0x24523a7e,0xbbb5ba54,0xb576bb63,0x340e3ba3,0xb13bbbd3,0x2c9c3bf2,
  0x386abb3d,0xba2139f8,0x3b57b835,0xbbf13432,0x39e7bc00,0xb8d6adc9,0xbacb3bde,0x372c3457,0x3bdab962,0x3764bb35,0xb9c03122,0xbaf73bef,
  0x398b39cd,0x38fd3946,0x386538b2,0x37853815,0xba85b9c9,0xbb92bb1e,0xbbfebbdd,0xbbc2bbf5,0xb66b3682,0xbb01bb94,0x387fb371,0x3a2d3beb,
  0xbac7bb76,0x3a00ad33,0x36bb3bd4,0xbbeab79b,0xbc0026ad,0x3bf32c38,0xbbd6b109,0x3ba733eb,0x3153bbff,0xb70a3b9e,0x396bba9b,0xbade390c,
  0xb5d4b5bc,0xbbb03b2c,0x32013830,0x3bf6ba67,0x3bccbb52,0x2c06b92e,0xbb83385f,0xb8c73bab,0xb9c5b982,0xba41ba04,0xbab0ba7a,0xbb10bae1,
  0xb8a3b986,0xb52fb74e,0xa94db1e8,0x33d32e91,0xbb54bb4f,0x37bdb523,0x3a9e3bc8,0xb916308d,0x3840b5c8,0x394a3bf9,0xbb42b294,0xb0a6bb0a,
  0x251bbbff,0xaf273bfc,0x327cbbe6,0xb4ab3bc0,0x3be325e4,0xbb2fb4e7,0x39e33884,0xb81aba35,0x3b73bb78,0xb46fb715,0xbbdc3ad1,0x2e2d38cc,
  0x33283676,0x3bfcba19,0x3581bab3,0xba6b3493,0x363136dd,0x34cf3581,0x32c6341a,0x2fbd3153,0xbae1bb65,0xb970ba39,0xb715b889,0xb16cb4f3,
  0xb9a12a7a,0xb924bbfe,0x3a933042,0x37dd3bcc,0x308db9aa,0x3b453b07,0xb94632ad,0xb845bbfa,0xbb68b55e,0x3b1836bb,0xbabab805,0x3a4d38a3,
  0x3bc0b625,0xbbfe2ec3,0x3b9431cf,0xba89b742,0x9cb6b95d,0xbbf8396b,0xb1b63a5c,0x3bb5b840,0x38cc9648,0x3b81bbac,0xac38b85a,0xbbce3933,
  0xbb60bb3a,0xbba1bb83,0xbbd2bbbc,0xbbf1bbe3,0x3815361a,0x39df3907,0x3b2c3a97,0x3be23b9c,0xb9afbbfd,0x3a21294d,0x388e3bee,0xbaf7b328,
  0x3beb39a6,0xb6af37a6,0xba04bbd3,0x3ac42d00,0x360ebb89,0xb7643b42,0x3855baeb,0xb8ee3a85,0x33eb3b63,0x28e8bbf5,0xb5233bde,0x389ebb21,
  0x3c00b9f0,0x2d97b9e3,0xbbdf38db,0xb44b3ac7,0xba673c00,0x358d3487,0x3bfcbab6,0x330fba15,0x3b7a3bf1,0x394a3a93,0x33893764,0xb3d39cb6,
  0x3afb3be2,0x35eb3946,0xb4c328e8,0xbaa9b8cc,0x27763af7,0xbb2fbaba,0x3a76ad97,0x30a63b60,0xaf8b3ac4,0xb994bb94,0x3bf8358d,0xb8743815,
  0xbb4c38ee,0x3bfcb1b6,0xbad5b4cf,0x381a39af,0xbbb3389e,0x3b592c38,0xb76fb970,0xb24b3beb,0xb9d2344b,0xbb923bd2,0xb0f03924,0x3a6bb60e,
  0xb8f3330f,0xbc003b2c,0xb91f3b45,0x323233eb,0xb5b1afbd,0xba00b88e,0xbbc6bb18,0xbbc2bc00,0xb7d2b16c,0xbb6fba04,0xbba3bbfe,0xb86fba67,
  0xbbffb7dd,0x370ab855,0x38b73bf8,0xbbeab631,0xbbf2b845,0x39bcb523,0x2dc93b81,0xbaa5bae1,0xb68dba4d,0xac063bdf,0x382abba1,0xbade39a1,
  0xb457ba89,0xb6543bfc,0x3b16b9df,0xbbd8308d,0x397dbbb5,0xb52fb2c6,0xbbe73a21,0xb8c73b68,0x3a49bbce,0x2311b715,0xba2536af,0xbbd93bc0,
  0xb958b785,0xbb81ba9e,0xbbefbbf3,0xba89bb73,0xbbf7bbc2,0xb9b8bb42,0xaf59b70a,0x384a3328,0xbb8bba2d,0x39dfb27c,0x34263bb0,0xbbceb98b,
  0xb4b7bbea,0x3b6c39e3,0xbafe2c06,0x3185ba85,0xaadebba7,0xb6af3bdc,0x3a58ba41,0xbbe2366b,0x3a29bade,0xbc003581,0x3a45352f,0xb2f7bac7,
  0x3b37bbf6,0x28e8b865,0xbaee37bd,0xbac43c00,0x3b13b8c7,0x3b5cbbfe,0x3463b94a,0xb8993153,0xb9f4bb10,0xb58db87f,0x3029af27,0x389e35d4,
  0x2dfbb3d3,0x399936bb,0x3bf23b2f,0x3ac13bcc,0x3552b916,0x39703bd6,0xbbbab46f,0x330fb9c5,0x3ba530a6,0xb5f7396b,0xb7c8bbfc,0x3be138a3,
  0x3bfdb4ab,0xbb45b201,0x38e038fd,0xb16cbb54,0x391b381a,0xa17fbb83,0xb8f83b92,0x3bcfb840,0x36e82e2d,0x3bfebab0,0x37febb01,0xb845251b,
  0xb77a3a6b,0x3648294d,0x3bb2ba00,0x3a8cbbe3,0xb742b93c,0x2311b340,0x37a6340e,0x3aa93966,0x3b963a4d,0x3b7f3c00,0x380f3a21,0xb0be3219,
  0x3933b50b,0x35eb3be4,0xbbf5b8d6,0x3874b6c6,0x39413bb5,0xbbffb65f,0x38d1b764,0x33ba3bd7,0x3b9c2c9c,0xb994b83a,0x34873ae8,0x324bbbfe,
  0xb7213bf1,0x3b47b990,0xbbbf2d97,0x38c1387a,0x2d00372c,0x3b59b8a8,0x3a39bbed,0xb232b576,0xbbfb3af7,0xb9743b71,0x307434cf,0x3adbb86a,
  0x3b213a0d,0x3c003bcb,0x3b073bbd,0x386f39e7,0x351738ee,0xb599a452,0xbae5b924,0xbbe9bbda,0x3a153b98,0xbb6fb13b,0x2ec3ba60,0x3aa53b3f,
  0xba09344b,0xa884bb57,0x3a643b18,0xbbc3b263,0xb4f33bfb,0x39bcbacb,0xbbac380a,0x3bd8a9b1,0xbb2aafbd,0x36a439c0,0x3402bbf8,0xba6f3aa2,
  0xbbfa3b27,0xb6543a81,0x3907b05b,0x3bd9bb85,0x2c6ab7dd,0xb9da35df,0xbbec3ba1,0xb8203aac,0x3bf53b87,0x3b6c3bec,0x392e3a7e,0x32f73721,
  0xb9e7b785,0xbbfcbb5e,0xba81bbb0,0xb43eb894,0x379b3bfe,0xbc00b80f,0x374eb835,0x38993bfb,0xbb3fba2d,0x3b329fdb,0xb3403a41,0xb8eabbd0,
  0xb90c3b3d,0x3b5cb8d1,0xbbf93122,0x3ac13517,0x29b1bba7,0xb94f3b6a,0x3be4b7bd,0xbaf4b19e,0xbbab3962,0xb9993bbf,0x34e73359,0x3be1ba09,
  0x3b85bbf6,0x353ab99d,0xb83a2f27,0xbbf03abd,0x2e91356a,0xb5f7b074,0xba19b8ad,0xbbcfbb2a,0xb966bb10,0xaba7b63c,0x38a8346f,0x3bb73a90,
  0xbb0aaa16,0xa17fbae5,0x3b1e3ace,0xba8c2c6a,0x36c6b916,0x36ff3c00,0xbbcbb8fd,0x3a50b2de,0xba35b6d2,0x36483a64,0x2d33bbe5,0xb84a3b96,
  0x3bfeb4ab,0xb9fcb602,0x313b3b01,0x37e8bbe0,0x3493b9eb,0xb9b83402,0xbb9e3bc9,0xb1853941,0x35762e2d,0x3b90b9b3,0x3acbbbf3,0x2fefb850,
  0x3a543bcf,0x2884374e,0xb9f8b648,0xbbe9bbab,0x398b3bb7,0xb4db3340,0xbbdcb9fc,0xb911bb85,0xb4323a8c,0xb6a4bbf9,0x3b3539b8,0xbbc3ae91,
  0xb66b3a50,0xad65bbe4,0x38653b90,0xbb0db966,0xbbef384a,0x39da34e7,0x2b43bb6c,0xba6f3b0a,0xbc0037e8,0x3759383a,0x387fbbfc,0xbbf636c6,
  0xb7f33185,0xbb7f3a19,0xbb8e3c00,0xb8203a35,0xb5d42fef,0xba1d38a8,0xbbd63b32,0xbba93bfe,0xb8e5b2f7,0xbbffbb1e,0xb954bb5c,0x30beb493,
  0xb9c5b43e,0xbb9fbbcb,0xb201b94f,0x3a313576,0xbbb8b899,0x3b47ad33,0xb6f43999,0xb3babbf5,0xbb54b8ea,0x3bf9313b,0xbab0353a,0x3790b9e7,
  0xb010bac1,0xb9743b9e,0x3bfdb5f7,0xb8c1b79b,0x251bbaf4,0xbb1b3acb,0x3a9e2ba7,0x2e5fbb3f,0x3af1bbe1,0x3599b92e,0xb546a17f,0xbadb390c,
  0x3b73bbf0,0x3929ba81,0x327cb6ff,0xb49f29b1,0xb825baa9,0x353aaec3,0x3b7c3994,0x3af43bfa,0x360eb0be,0x3bf43a64,0x388e3b47,0xb7372c6a,
  0x38bcb874,0x2ba73bac,0xb979bb59,0x3bf03742,0x3c0033ba,0xbb043402,0x3855b974,0xacce3b96,0x3bc5b24b,0xb6ffb907,0xb6993c00,0x3bb7b933,
  0x363138c1,0x3902bbec,0xbbdf3599,0x34ff3941,0x30d73232,0x39fcb7a6,0x3bffbb6f,0x3a50bb9c,0xb9a13adb,0xb47b380f,0x32c62884,0x3937b721,
  0x3ad8386f,0x3b903bf5,0x35a539bc,0xb7e8ad00,0x3b683be9,0x2ef538d1,0xba93b6a4,0xbb24bbfb,0x3a733aa5,0xbbfcb487,0x39d6b654,0xafef3b21,
  0x1cb63bc3,0xb7b2bbbf,0x3aba39da,0xbbfab517,0xb3a23bd8,0x3b32ba39,0xbb4a2311,0x343e3a15,0xbb603a6f,0x3a3d3074,0x31b6bb7f,0xbb9a3a09,
  0xbbe83bd9,0xb94f3b07,0xa81f35eb,0x38eab4f3,0xb9af3820,0xbbae3ae5,0xbbd23bff,0xba113b2a,0x319e389e,0xb929b426,0xbc00bb45,0xb911bb37,
  0xbbffbac1,0xb805bafe,0x382a217f,0x3bfd3b13,0xbabd330f,0x34dbba58,0x36023bfe,0xbb0db9f4,0xb68dbbe1,0x3a5c3a45,0xbbe7b648,0x3b89adfb,
  0xba90b16c,0x2d653aee,0x39b3bb81,0xbbf63552,0x397dbbcf,0xbbbc3463,0x338939b8,0x39f0bba5,0x32deb845,0xb7593029,0xbb5e39df,0xbba93bfd,
  0x3b7aba8c,0x3beebbf2,0x3a76bb6c,0x36ddb91b,0xbbe0ba89,0xba1dbbba,0x1fdbb6af,0x3a3136e8,0xa776b84a,0x3aeb37c8,0x3ad53c00,0xaa7a377a,
  0xb850bbce,0x3b9f38e0,0xbb6a28e8,0x3790b958,0x3b4cb185,0xb8db38f8,0x30f0bb5c,0x355e3bf7,0x3894bbe2,0xbbf937fe,0x399d358d,0x2e5fbb8b,
  0x39d232f7,0x341abbb2,0xbbc63999,0x395d34b7,0x3bd0bac4,0x3b1bbbef,0x363cb970,0xb49faade,0xb5b13899,0x30422f59,0x38b7b5f7,0x3b3aba29,
  0x3219b3d3,0x3b0438b7,0x3b713bfc,0x34ff397d,0x36e83aa9,0xb8b2adc9,0xbbefbb59,0xb5bcba49,0x3bd730a6,0xb902382a,0xa452bb92,0x39373b7a,
  0xb9583874,0x3371bb16,0x34263c00,0xb982bafb,0x387a381a,0x347bbbe7,0xbb573a00,0x3b242776,0xbb8b324b,0x31093a25,0x3a58bb6f,0xbb4f2f8b,
  0xb86a3a6b,0x2ef53389,0x39c0b70a,0x3bfabb4c,0xaadeb232,0xb83034c3,0xbaee39bc,0xbbff3bb3,0x3bda3bc2,0x37b23a76,0xb5df2c06,0xbb9ab9d2,
  0xbb37b86f,0xba7abbf8,0x3029b654,0x3b7838f3,0x32633bea,0xba3dbad5,0x3c00352f,0xba1135b1,0xb9f4baa5,0x3bc8376f,0xbbba2311,0x39cdb7d2,
  0xbaa23ade,0x3baeb0f0,0xb65fb94a,0xb7373bff,0x3552bbd8,0xbbe6391f,0x38e035eb,0x3682bbf2,0xbaac38c7,0xbbf43bc6,0xb9903b2f,0xacce368d,
  0x3bfdbbd9,0x3ad1bba3,0x37feb994,0x26adb457,0x38a33b9a,0xb8dba452,0xbb83bbae,0x2a7ab86a,0x37423b78,0xbab6b426,0xb907bbe6,0x39aa2ade,
  0xb8403a11,0x341abb57,0x294d3bf4,0xb55ebbda,0xb93339cd,0x3889ba58,0xb7a63ad1,0x3625bb37,0xbbe33737,0x304239c0,0x3b42bb04,0xb95db263,
  0xbb9c3682,0xb2ad3aee,0x3bf5b8b2,0x1648b9f4,0xb3282cce,0xb80535df,0xb9e33902,0xbb3a3aa2,0xad0026ad,0xb1cf3029,0xb4873371,0xb61a3552,
  0xba85b4ff,0xba5cbc00,0x3581b47b,0x3bfd3aac,0xbb21b5bc,0xb85abbba,0x3a393109,0x39a63bfd,0xbac7b937,0x3bbc365f,0xbbfeaef5,0x3b89b219,
  0xba15b982,0x3a9738e0,0xbb07b830,0x3b6336e8,0x3153bb24,0xbbee3990,0x36bb37b2,0x39f0bbd7,0x34f3bb4f,0xbbd337fe,0xaec33a7a,0x3c00b958,
  0x3bccbbfa,0x3aebbb71,0x396bba3d,0x36ddb87a,0x3bfabbff,0x3bdebbef,0x3bacbbc8,0x3b65bb8b,0x3bc03911,0x38303b6a,0xb946ad65,0xbb4fbbd0,
  0x3a353bfd,0xb85f30f0,0xbb1ebbbc,0x35c8b5b1,0x38cc3b0d,0xba7ab99d,0x3b943759,0xbbffb19e,0xb4933b89,0x31e8bbc6,0xad333bee,0xa5e4bbff,
  0xb8153bf6,0x3bc8b63c,0xac38ba1d,0xbb783abd,0xbbf539f0,0x329438b7,0x3b9ebaeb,0xb676b68d,0xbbeb3ba9,0xbbe63c00,0xbb2c3b9f,0xb9cd3a90,
  0xb79b36dd,0xb884382a,0xb92e38db,0xb9c9397d,0x33eb3a31,0xbad1b602,0xba04bbf9,0x3682b2de,0xb90c2a7a,0xbab3bbe7,0x374eb41a,0x3b763b7a,
  0xba673790,0x38b2b9b3,0xb5233b1b,0x26adbbe0,0xbbabb55e,0x3bdd3389,0xbbf9b042,0x3bff2776,0xbae12e5f,0xb3713b5e,0x3bfcb929,0xb5bcb850,
  0xae91b95d,0xbbd43a76,0x34e73805,0x3b52bb4c,0x308db49f,0xb1091fdb,0xb71534db,0xb9823894,0x3b0abb3a,0x3a9bbad5,0x3a19ba5c,0x3986b9d2,
  0x2f8bb7e8,0x3bde3979,0x376f3b32,0xb9aab0d7,0x3bb83b24,0xb1223855,0xbbfdba3d,0xaa16b9a1,0x3bb3afef,0xbab63699,0x391fb94f,0xb6253ad8,
  0x30103bfa,0xb359bbdf,0x35463bae,0xb6d2bb68,0x38f3343e,0x3889bbff,0xbba3353a,0x96483a73,0xbaf13b9a,0x38ad32c6,0x39f8bbf4,0xb9eb9cb6,
  0xb7d238ea,0xb2ad35a5,0x2dc92ba7,0x361ab3a2,0xba543a11,0xbace3a93,0xbb353b04,0xbb873b60,0x3bf23af4,0x31cf39d6,0xbb16b6ff,0xb9a6bbe8,
  0xb4323737,0xbbe5baba,0x2b43b902,0x3bfe39af,0x34573bf0,0xb85abb4a,0x3a2539fc,0xbb63b825,0xbbef2cce,0x3bc9b1b6,0xbb8e347b,0x3b3db60e,
  0xba493bb7,0x3a97a81f,0x34c3bb90,0xbc0038bc,0xb7f3b4ff,0xba7e3bd2,0x39542ef5,0x3962bc00,0xbafb3a50,0xbbd33b7c,0xbbf83bfc,0xbb653bc5,
  0x38e5b937,0x3835b88e,0x36f4b7b2,0x356ab631,0xbb13bbe9,0x31e8b6f4,0x3bf239da,0x36763af1,0x3be83911,0x340e3ab0,0xbb7cb759,0xb72cbb73,
  0x2dfbbbc3,0x32943bfd,0xb7c8bb7f,0x39c93a54,0x38253b0d,0xb8d6ba9e,0x39793a1d,0xba0db98b,0x3ba5ba6f,0xb884b546,0xb8f83bff,0x3b76b432,
  0xb8bc3bf6,0x3ae8b27c,0x3699bb9f,0xbb98366b,0x391bb820,0x3ab3b9f8,0x3bb2bb47,0x3bffbbef,0xbbc53ba9,0xbbed3bdc,0xbbff3bf9,0xbbfb3c00,
  0x377ab0be,0x3bdd3b35,0x2f593974,0xbb52b7f3,0x30d73a31,0xbbbdb865,0xb5a5bb1b,0x3b2735d4,0x3bf733ba,0xbbd42b43,0x3afeb599,0xb98638e5,
  0xbad83790,0x3a60b87f,0xb9d63929,0x393cb9c5,0x34b738c1,0x3a9bbb8e,0xba45a884,0xb5c83bb8,0xba732e5f,0xb80a3bd6,0x3b4ab4db,0x350bbb54,
  0xba293adb,0xb85f3954,0xb46336a4,0x25e43010,0x33a2b49f,0x305bb201,0x281fad65,0xac9c251b,0x3f803f80,0x3f803f80,0x3f803f80,0x3f803f80,
  0x3f803f80,0x3f803f80,0x3f803f80,0x3f803f80,0x3f803f80,0x3f803f80,0x3f803f80,0x3f803f80,0x3f803f80,0x3f803f80,0x3f803f80,0x3f803f80,
  0x3f803f80,0x3f803f80,0x3f803f80,0x3f803f80,0x3f803f80,0x3f803f80,0x3f803f80,0x3f803f80,0x3f803f80,0x3f803f80,0x3f803f80,0x3f803f80,
  0x3f803f80,0x3f803f80,0x3f803f80,0x3f803f80,0x3f803f80,0x3f803f80,0x3f803f80,0x3f803f80,0x3f803f80,0x3f803f80,0x3f803f80,0x3f803f80,
  0x3f803f80,0x3f803f80,0x3f803f80,0x3f803f80,0x3f803f80,0x3f803f80,0x3f803f80,0x3f803f80,0x3f803f80,0x3f803f80,0x3f803f80,0x3f803f80,
  0x3f803f80,0x3f803f80,0x3f803f80,0x3f803f80,0x3f803f80,0x3f803f80,0x3f803f80,0x3f803f80,0x3f803f80,0x3f803f80,0x3f803f80,0x3f803f80,
  0x3f803f80,0x3f803f80,0x3f803f80,0x3f803f80,0x3f803f80,0x3f803f80,0x3f803f80,0x3f803f80,0x3f803f80,0x3f803f80,0x3f803f80,0x3f803f80,
  0x3f803f80,0x3f803f80,0x3f803f80,0x3f803f80,0x3f803f80,0x3f803f80,0x3f803f80,0x3f803f80,0x3f803f80,0x3f803f80,0x3f803f80,0x3f803f80,
  0x3f803f80,0x3f803f80,0x3f803f80,0x3f803f80,0x3f803f80,0x3f803f80,0x3f803f80,0x3f803f80,0x3f803f80,0x3f803f80,0x3f803f80,0x3f803f80,
  0x3f803f80,0x3f803f80,0x3f803f80,0x3f803f80,0x3f803f80,0x3f803f80,0x3f803f80,0x3f803f80,0x3f803f80,0x3f803f80,0x3f803f80,0x3f803f80,
  0x3f803f80,0x3f803f80,0x3f803f80,0x3f803f80,0x3f803f80,0x3f803f80,0x3f803f80,0x3f803f80,0x3f803f80,0x3f803f80,0x3f803f80,0x3f803f80,
  0x3f803f80,0x3f803f80,0x3f803f80,0x3f803f80,0x3f803f80,0x3f803f80,0x3f803f80,0x3f803f80,0x3f803f80,0x3f803f80,0x3f803f80,0x3f803f80,
  0x3f803f80,0x3f803f80,0x3f803f80,0x3f803f80,0x3f803f80,0x3f803f80,0x3f803f80,0x3f803f80,0x3f803f80,0x3f803f80,0x3f803f80,0x3f803f80,
  0x3f803f80,0x3f803f80,0x3f803f80,0x3f803f80,0x3f803f80,0x3f803f80,0x3f803f80,0x3f803f80,0x3f803f80,0x3f803f80,0x3f803f80,0x3f803f80,
  0x3f803f80,0x3f803f80,0x3f803f80,0x3f803f80,0x3f803f80,0x3f803f80,0x3f803f80,0x3f803f80,0x3f803f80,0x3f803f80,0x3f803f80,0x3f803f80,
  0x3f803f80,0x3f803f80,0x3f803f80,0x3f803f80,0x3f803f80,0x3f803f80,0x3f803f80,0x3f803f80,0x3f803f80,0x3f803f80,0x3f803f80,0x3f803f80,
  0x3f803f80,0x3f803f80,0x3f803f80,0x3f803f80,0x3f803f80,0x3f803f80,0x3f803f80,0x3f803f80,0x3f803f80,0x3f803f80,0x3f803f80,0x3f803f80,
  0x3f803f80,0x3f803f80,0x3f803f80,0x3f803f80,0x3f803f80,0x3f803f80,0x3f803f80,0x3f803f80,0x3f803f80,0x3f803f80,0x3f803f80,0x3f803f80,
  0x3f803f80,0x3f803f80,0x3f803f80,0x3f803f80,0x3f803f80,0x3f803f80,0x3f803f80,0x3f803f80,0x3f803f80,0x3f803f80,0x3f803f80,0x3f803f80,
  0x3f803f80,0x3f803f80,0x3f803f80,0x3f803f80,0x3f803f80,0x3f803f80,0x3f803f80,0x3f803f80,0x3f803f80,0x3f803f80,0x3f803f80,0x3f803f80,
  0x3f803f80,0x3f803f80,0x3f803f80,0x3f803f80,0x3f803f80,0x3f803f80,0x3f803f80,0x3f803f80,0x3f803f80,0x3f803f80,0x3f803f80,0x3f803f80,
  0x3f803f80,0x3f803f80,0x3f803f80,0x3f803f80,0x3f803f80,0x3f803f80,0x3f803f80,0x3f803f80,0x3f803f80,0x3f803f80,0x3f803f80,0x3f803f80,
  0x3f803f80,0x3f803f80,0x3f803f80,0x3f803f80,0x3f803f80,0x3f803f80,0x3f803f80,0x3f803f80,0x3f803f80,0x3f803f80,0x3f803f80,0x3f803f80,
  0x3f803f80,0x3f803f80,0x3f803f80,0x3f803f80,0x3f803f80,0x3f803f80,0x3f803f80,0x3f803f80,0x3f803f80,0x3f803f80,0x3f803f80,0x3f803f80,
  0x3f803f80,0x3f803f80,0x3f803f80,0x3f803f80,0x3f803f80,0x3f803f80,0x3f803f80,0x3f803f80,0x3f803f80,0x3f803f80,0x3f803f80,0x3f803f80,
  0x3f803f80,0x3f803f80,0x3f803f80,0x3f803f80,0x3f803f80,0x3f803f80,0x3f803f80,0x3f803f80,0x3f803f80,0x3f803f80,0x3f803f80,0x3f803f80,
  0x3f803f80,0x3f803f80,0x3f803f80,0x3f803f80,0x3f803f80,0x3f803f80,0x3f803f80,0x3f803f80,0x3f803f80,0x3f803f80,0x3f803f80,0x3f803f80,
  0x3f803f80,0x3f803f80,0x3f803f80,0x3f803f80,0x3f803f80,0x3f803f80,0x3f803f80,0x3f803f80,0x3f803f80,0x3f803f80,0x3f803f80,0x3f803f80,
  0x3f803f80,0x3f803f80,0x3f803f80,0x3f803f80,0x3f803f80,0x3f803f80,0x3f803f80,0x3f803f80,0x3f803f80,0x3f803f80,0x3f803f80,0x3f803f80,
  0x3f803f80,0x3f803f80,0x3f803f80,0x3f803f80,0x3f803f80,0x3f803f80,0x3f803f80,0x3f803f80,0x3f803f80,0x3f803f80,0x3f803f80,0x3f803f80,
  0x3f803f80,0x3f803f80,0x3f803f80,0x3f803f80,0x3f803f80,0x3f803f80,0x3f803f80,0x3f803f80,0x3f803f80,0x3f803f80,0x3f803f80,0x3f803f80,
  0x3f803f80,0x3f803f80,0x3f803f80,0x3f803f80,0x3f803f80,0x3f803f80,0x3f803f80,0x3f803f80,0x3f803f80,0x3f803f80,0x3f803f80,0x3f803f80,
  0x3f803f80,0x3f803f80,0x3f803f80,0x3f803f80,0x3f803f80,0x3f803f80,0x3f803f80,0x3f803f80,0x3f803f80,0x3f803f80,0x3f803f80,0x3f803f80,
  0x3f803f80,0x3f803f80,0x3f803f80,0x3f803f80,0x3f803f80,0x3f803f80,0x3f803f80,0x3f803f80,0x3f803f80,0x3f803f80,0x3f803f80,0x3f803f80,
  0x3f803f80,0x3f803f80,0x3f803f80,0x3f803f80,0x3f803f80,0x3f803f80,0x3f803f80,0x3f803f80,0x3f803f80,0x3f803f80,0x3f803f80,0x3f803f80,
  0x3f803f80,0x3f803f80,0x3f803f80,0x3f803f80,0x3f803f80,0x3f803f80,0x3f803f80,0x3f803f80,0x3f803f80,0x3f803f80,0x3f803f80,0x3f803f80,
  0x3f803f80,0x3f803f80,0x3f803f80,0x3f803f80,0x3f803f80,0x3f803f80,0x3f803f80,0x3f803f80,0x3f803f80,0x3f803f80,0x3f803f80,0x3f803f80,
  0x3f803f80,0x3f803f80,0x3f803f80,0x3f803f80,0x3f803f80,0x3f803f80,0x3f803f80,0x3f803f80,0x3f803f80,0x3f803f80,0x3f803f80,0x3f803f80,
  0x3f803f80,0x3f803f80,0x3f803f80,0x3f803f80,0x3f803f80,0x3f803f80,0x3f803f80,0x3f803f80,0x3f803f80,0x3f803f80,0x3f803f80,0x3f803f80,
  0x3f803f80,0x3f803f80,0x3f803f80,0x3f803f80,0x3f803f80,0x3f803f80,0x3f803f80,0x3f803f80,0x3f803f80,0x3f803f80,0x3f803f80,0x3f803f80,
  0x3f803f80,0x3f803f80,0x3f803f80,0x3f803f80,0x3f803f80,0x3f803f80,0x3f803f80,0x3f803f80,0x3f803f80,0x3f803f80,0x3f803f80,0x3f803f80,
  0x3f803f80,0x3f803f80,0x3f803f80,0x3f803f80,0x3f803f80,0x3f803f80,0x3f803f80,0x3f803f80,0x3f803f80,0x3f803f80,0x3f803f80,0x3f803f80,
  0x3f803f80,0x3f803f80,0x3f803f80,0x3f803f80,0x3f803f80,0x3f803f80,0x3f803f80,0x3f803f80,0x3f803f80,0x3f803f80,0x3f803f80,0x3f803f80,
  0x3f803f80,0x3f803f80,0x3f803f80,0x3f803f80,
};

__device__ __align__(128) float    g_part[16][8][2176];
__device__ __align__(128) float    g_kv[16][2176];
constexpr int OBLK = 16 * 1024 + 32;
__device__ __align__(128) uint4    g_o[16 * OBLK];
#define GSTAMP(role, i) do {} while (0)
#define STAMP(role, i) do {} while (0)
#define PDUMP(role) do {} while (0)
#define PROF_SMEM 0

constexpr int STAGE_BYTES = 57344;
constexpr int OFF_H = 4 * 16384, OFF_VP = 9 * 16384, OFF_SPARE = 10 * 16384;
constexpr int OFF_XT = 172032, XT_STRIDE = 4112;
constexpr int OFF_BAR = 204928, OFF_EPOCH = OFF_BAR + 640, OFF_EX = OFF_BAR + 656, OFF_D = OFF_BAR + 672, OFF_SCALE = OFF_BAR + 704;
constexpr int OFF_F2F = 205824, OFF_F2I = 207872, OFF_F4 = 209920, OFF_ONES = 214016, OFF_KVB = 214016;
constexpr int OFF_STG = 219136, STG_STRIDE = 4352, SMEM_TOTAL = 232192 + PROF_SMEM;
enum { B_FULL1 = 0, B_EMPTY1 = 3, B_Q = 6, B_ODONE1 = 7, B_O1RDY = 8, B_H = 9, B_XRAW = 10, B_XT = 11, B_KV = 12, B_Y = 13,  B_AFREE = 15,
       B_STG = 18, B_ODONE = 24, B_XFREE = 25, B_FULL2 = 33, B_CONS2 = 49, B_SFREE = 14, B_KV1 = 61, B_PKRDY = 62, B_PKFREE = 64, B_H2 = 65, B_G1DONE = 66, B_COUNT = 67, B_FIRST = 67 };
constexpr uint64_t SLOT_A = 0x6859468594685948ull, SLOT_B = 0x7103271032710326ull;
constexpr int NPRE = 6, BEARLY = 3;
__host__ __device__ constexpr int bar_count(int i) {
  return i < B_EMPTY1 ? 1 : i < B_Q ? 4 : i == B_XT ? 4 : i == B_H ? 4 : (i == B_SFREE || i == B_G1DONE) ? 2 : i >= B_PKFREE ? 4 : i >= B_PKRDY ? 8 : i == B_Y ? 9
       : (i >= B_AFREE && i < B_STG) ? 16 : (i == B_ODONE || i == B_ODONE1) ? 8 : (i >= B_XFREE && i < B_FULL2) ? 4
       : i == B_KV1 ? 1 : i >= B_CONS2 ? 4 : (i >= B_FULL2 && i < B_FULL2 + NPRE) ? 2 : 1;
}
__host__ __device__ constexpr uint64_t bar_counts(int r) {
  uint64_t v = 0;
  for (int w = 0; w < 11; w++) v |= (uint64_t)(bar_count(1 + 11 * r + w) - 1) << (4 * w);
  return v;
}
constexpr uint32_t SW128 = 64 | (1u << 30);
constexpr int SPIN_LIMIT = 1 << 22;
#define SPLIT0 2
#define PFD 3
#define PD1 700
#define PD2 450
#define QPF 6
#define BPACE 250
#define OCH 3
#define O1D 1
#define HOLD2 12
#define D1 100
#define TRICK 3
#define HSTART 1500
#define PACE 800

__device__ __forceinline__ uint32_t smem_u32(const void* p) { return (uint32_t)__cvta_generic_to_shared(p); }
__device__ __forceinline__ void wg_fence() { asm volatile("wgmma.fence.sync.aligned;" ::: "memory"); }
__device__ __forceinline__ void wg_commit() { asm volatile("wgmma.commit_group.sync.aligned;" ::: "memory"); }
template <int N> __device__ __forceinline__ void wg_wait() { asm volatile("wgmma.wait_group.sync.aligned %0;" ::"n"(N) : "memory"); }
template <int N> __device__ __forceinline__ void keep(float (&d)[N]) {
#pragma unroll
  for (int i = 0; i < N; i++) asm volatile("" : "+f"(d[i])::"memory");
}
__device__ __forceinline__ void mbar_init(uint32_t bar, int cnt) { asm volatile("mbarrier.init.shared::cta.b64 [%0], %1;" ::"r"(bar), "r"(cnt)); }
__device__ __forceinline__ void mbar_expect(uint32_t bar, int bytes) { asm volatile("mbarrier.arrive.expect_tx.shared::cta.b64 _, [%0], %1;" ::"r"(bar), "r"(bytes) : "memory"); }
__device__ __forceinline__ void mbar_arrive(uint32_t bar) { asm volatile("mbarrier.arrive.shared::cta.b64 _, [%0];" ::"r"(bar) : "memory"); }
__device__ __forceinline__ void mbar_arrive_cl(uint32_t bar, uint32_t cta) {
  asm volatile("{\n.reg .b32 r;\nmapa.shared::cluster.u32 r, %0, %1;\nmbarrier.arrive.shared::cluster.b64 _, [r];\n}\n" ::"r"(bar), "r"(cta) : "memory");
}
__device__ __forceinline__ void mbar_wait(uint32_t bar, uint32_t parity) {
  asm volatile("{\n.reg .pred p;\n.reg .u32 n;\nmov.u32 n, 0;\n"
               "W_%=:\nmbarrier.try_wait.parity.shared::cta.b64 p, [%0], %1;\n@p bra D_%=;\n"
               "add.u32 n, n, 1;\nsetp.lt.u32 p, n, %2;\n@p bra W_%=;\ntrap;\nD_%=:\n}\n" ::"r"(bar), "r"(parity), "n"(SPIN_LIMIT) : "memory");
}
__device__ __forceinline__ void fence_async() { asm volatile("fence.proxy.async.shared::cta;" ::: "memory"); }
__device__ __forceinline__ void bar_sync(int id) { asm volatile("bar.sync %0, 128;" ::"r"(id) : "memory"); }
__device__ __forceinline__ void tma2d(uint32_t dst, const CUtensorMap* m, int c0, int c1, uint32_t bar) {
  asm volatile("cp.async.bulk.tensor.2d.shared::cluster.global.mbarrier::complete_tx::bytes [%0], [%1, {%3, %4}], [%2];"
               ::"r"(dst), "l"(m), "r"(bar), "r"(c0), "r"(c1) : "memory");
}
__device__ __forceinline__ void tma2d_mc(uint32_t dst, const CUtensorMap* m, int c0, int c1, uint32_t bar) {
  asm volatile("cp.async.bulk.tensor.2d.shared::cluster.global.mbarrier::complete_tx::bytes.multicast::cluster [%0], [%1, {%3, %4}], [%2], %5;"
               ::"r"(dst), "l"(m), "r"(bar), "r"(c0), "r"(c1), "h"((uint16_t)3) : "memory");
}
__device__ __forceinline__ void tma3d(uint32_t dst, const CUtensorMap* m, int c0, int c1, int c2, uint32_t bar) {
  asm volatile("cp.async.bulk.tensor.3d.shared::cluster.global.mbarrier::complete_tx::bytes [%0], [%1, {%3, %4, %5}], [%2];"
               ::"r"(dst), "l"(m), "r"(bar), "r"(c0), "r"(c1), "r"(c2) : "memory");
}
__device__ __forceinline__ void tma4d(uint32_t dst, const CUtensorMap* m, int c0, int c1, int c2, int c3, uint32_t bar) {
  asm volatile("cp.async.bulk.tensor.4d.shared::cluster.global.mbarrier::complete_tx::bytes [%0], [%1, {%3, %4, %5, %6}], [%2];"
               ::"r"(dst), "l"(m), "r"(bar), "r"(c0), "r"(c1), "r"(c2), "r"(c3) : "memory");
}
__device__ __forceinline__ void bulk_ld(uint32_t dst, const void* src, int bytes, uint32_t bar) {
  asm volatile("cp.async.bulk.shared::cluster.global.mbarrier::complete_tx::bytes [%0], [%1], %2, [%3];" ::"r"(dst), "l"(src), "r"(bytes), "r"(bar) : "memory");
}
__device__ __forceinline__ void bulk_ld_mc(uint32_t dst, const void* src, int bytes, uint32_t bar) {
  asm volatile("cp.async.bulk.shared::cluster.global.mbarrier::complete_tx::bytes.multicast::cluster [%0], [%1], %2, [%3], %4;"
               ::"r"(dst), "l"(src), "r"(bytes), "r"(bar), "h"((uint16_t)3) : "memory");
}
__device__ __forceinline__ void tma2d_st(const CUtensorMap* m, uint32_t src, int c0, int c1) {
  asm volatile("cp.async.bulk.tensor.2d.global.shared::cta.bulk_group [%0, {%2, %3}], [%1];" ::"l"(m), "r"(src), "r"(c0), "r"(c1) : "memory");
}
__device__ __forceinline__ void ldsm4(uint32_t (&r)[4], uint32_t a) {
  asm volatile("ldmatrix.sync.aligned.m8n8.x4.shared.b16 {%0,%1,%2,%3}, [%4];" : "=r"(r[0]), "=r"(r[1]), "=r"(r[2]), "=r"(r[3]) : "r"(a) : "memory");
}
__device__ __forceinline__ void ldsm4t(uint32_t (&r)[4], uint32_t a) {
  asm volatile("ldmatrix.sync.aligned.m8n8.x4.trans.shared.b16 {%0,%1,%2,%3}, [%4];" : "=r"(r[0]), "=r"(r[1]), "=r"(r[2]), "=r"(r[3]) : "r"(a) : "memory");
}
__device__ __forceinline__ void stsm4(uint32_t a, uint32_t r0, uint32_t r1, uint32_t r2, uint32_t r3) {
  asm volatile("stmatrix.sync.aligned.m8n8.x4.shared.b16 [%0], {%1,%2,%3,%4};" ::"r"(a), "r"(r0), "r"(r1), "r"(r2), "r"(r3) : "memory");
}
__device__ __forceinline__ uint32_t pk2(float lo, float hi) { uint32_t r; asm("cvt.rn.bf16x2.f32 %0, %1, %2;" : "=r"(r) : "f"(hi), "f"(lo)); return r; }
__device__ __forceinline__ uint32_t hmul(uint32_t a, uint32_t b) { uint32_t r; asm("mul.rn.bf16x2 %0, %1, %2;" : "=r"(r) : "r"(a), "r"(b)); return r; }
__device__ __forceinline__ uint32_t hadd(uint32_t a, uint32_t b) { uint32_t r; asm("add.rn.bf16x2 %0, %1, %2;" : "=r"(r) : "r"(a), "r"(b)); return r; }
__device__ __forceinline__ uint32_t hmin(uint32_t a, uint32_t b) { uint32_t r; asm("min.bf16x2 %0, %1, %2;" : "=r"(r) : "r"(a), "r"(b)); return r; }
__device__ __forceinline__ uint32_t hmaxabs(uint32_t a, uint32_t b) { uint32_t r; asm("max.xorsign.abs.bf16x2 %0, %1, %2;" : "=r"(r) : "r"(a), "r"(b)); return r; }
__device__ __forceinline__ float ex2(float x) { float r; asm("ex2.approx.ftz.f32 %0, %1;" : "=f"(r) : "f"(x)); return r; }
__device__ __forceinline__ float rcp_fast(float x) { float r; asm("rcp.approx.ftz.f32 %0, %1;" : "=f"(r) : "f"(x)); return r; }
__device__ __forceinline__ uint32_t phi2(float lo, float hi) {
  uint32_t t;
  asm("cvt.rn.relu.bf16x2.f32 %0, %1, %2;" : "=r"(t) : "f"(hi), "f"(lo));
  const uint32_t e = pk2(ex2(lo * 1.4426950408889634f), ex2(hi * 1.4426950408889634f));
  return hadd(hadd(t, hmin(e, 0x3F803F80u)), 0x35863586u);
}
__device__ __forceinline__ bool opaque_true() { uint32_t v; asm volatile("mov.u32 %0, %%nctaid.y;" : "=r"(v)); return v != 0; }
__device__ __forceinline__ int norm_exp(uint32_t (&v)[32], float f0) {
  uint32_t m[4] = {hmaxabs(__float_as_uint(f0) >> 16, v[0]), v[1], v[2], v[3]};
#pragma unroll
  for (int i = 4; i < 32; i++) m[i & 3] = hmaxabs(m[i & 3], v[i]);
  m[0] = hmaxabs(hmaxabs(m[0], m[1]), hmaxabs(m[2], m[3]));
  const int e = min(max((int)(__reduce_max_sync(~0u, max(m[0] & 0x7FFFu, (m[0] >> 16) & 0x7FFFu)) >> 7), 1), 253);
  if (e > 141) {
#pragma unroll
    for (int i = 0; i < 32; i++) v[i] = hmul(v[i], 0x07000700u);
  }
  return e;
}
__device__ __forceinline__ void norm_cvt(uint32_t (&v)[32], float f0, int e) {
  const uint32_t sc = (e > 141 ? 255 - e : 142 - e) * 0x00800080u;
#pragma unroll
  for (int i = 0; i < 32; i++) {
    const uint32_t a = hmul(v[i], sc);
    v[i] = (a & 0x0FFF0FFFu) * 7 + a;
  }
  v[0] = __byte_perm(v[0], __half_as_ushort(__float2half_rn(f0 * __uint_as_float((254 - e) << 23))), 0x3254);
}
__device__ __forceinline__ void poll_ge(const unsigned* p, unsigned target) {
#pragma unroll 1
  for (int n = 0; n < SPIN_LIMIT; n++) {
    unsigned v;
    asm volatile("ld.relaxed.gpu.global.u32 %0, [%1];" : "=r"(v) : "l"(p) : "memory");
    if (__all_sync(~0u, (int)(v - target) >= 0)) { asm volatile("fence.acquire.gpu;" ::: "memory"); return; }
  }
  __trap();
}

__device__ __forceinline__ bool elect_one() {
  uint32_t p;
  asm volatile("{\n.reg .pred p;\nelect.sync _|p, 0xffffffff;\nselp.u32 %0, 1, 0, p;\n}\n" : "=r"(p));
  return p;
}
__device__ __forceinline__ uint4 ld_na4(const void* p) {
  uint4 v;
  asm volatile("ld.global.L1::no_allocate.v4.u32 {%0,%1,%2,%3}, [%4];" : "=r"(v.x), "=r"(v.y), "=r"(v.z), "=r"(v.w) : "l"(p) : "memory");
  return v;
}
__device__ __forceinline__ void st_cg4(void* p, uint4 v) {
  asm volatile("st.global.cg.v4.u32 [%0], {%1,%2,%3,%4};" ::"l"(p), "r"(v.x), "r"(v.y), "r"(v.z), "r"(v.w) : "memory");
}
__device__ __forceinline__ uint32_t mapa(uint32_t a, uint32_t cta) { uint32_t r; asm("mapa.shared::cluster.u32 %0, %1, %2;" : "=r"(r) : "r"(a), "r"(cta)); return r; }
__device__ __forceinline__ void st_async(uint32_t a, uint32_t v, uint32_t bar) {
  asm volatile("st.async.weak.shared::cluster.mbarrier::complete_tx::bytes.b32 [%0], %1, [%2];" ::"r"(a), "r"(v), "r"(bar) : "memory");
}
__device__ __forceinline__ void st_async4(uint32_t a, uint32_t x, uint32_t y, uint32_t z, uint32_t w, uint32_t bar) {
  asm volatile("st.async.weak.shared::cluster.mbarrier::complete_tx::bytes.v4.b32 [%0], {%1,%2,%3,%4}, [%5];" ::"r"(a), "r"(x), "r"(y), "r"(z), "r"(w), "r"(bar) : "memory");
}
__device__ __forceinline__ void tma3d_st(const CUtensorMap* m, uint32_t src, int c0, int c1, int c2) {
  asm volatile("cp.async.bulk.tensor.3d.global.shared::cta.bulk_group [%0, {%2, %3, %4}], [%1];" ::"l"(m), "r"(src), "r"(c0), "r"(c1), "r"(c2) : "memory");
}
__device__ __forceinline__ uint4 ld_rlx4(const void* p) {
  uint4 v;
  asm volatile("{\n.reg .b128 t;\n.reg .b64 a, b;\nld.relaxed.gpu.global.b128 t, [%4];\nmov.b128 {a, b}, t;\nmov.b64 {%0, %1}, a;\nmov.b64 {%2, %3}, b;\n}\n"
               : "=r"(v.x), "=r"(v.y), "=r"(v.z), "=r"(v.w) : "l"(p) : "memory");
  return v;
}
__device__ __forceinline__ void ld_stale4(uint4& v, const void* p, uint32_t tag) {
  asm volatile("{\n.reg .b128 t;\n.reg .b64 a, b;\n.reg .b32 x;\n.reg .pred p;\n"
               "lop3.b32 x, %0, %5, 1, 0x28;\nsetp.ne.u32 p, x, 0;\n"
               "mov.b64 a, {%0, %1};\nmov.b64 b, {%2, %3};\nmov.b128 t, {a, b};\n"
               "@p ld.relaxed.gpu.global.b128 t, [%4];\n"
               "mov.b128 {a, b}, t;\nmov.b64 {%0, %1}, a;\nmov.b64 {%2, %3}, b;\n}\n"
               : "+r"(v.x), "+r"(v.y), "+r"(v.z), "+r"(v.w) : "l"(p), "r"(tag) : "memory");
}
__device__ __forceinline__ void st_tag4(void* p, float a, float b, float c, float d, uint32_t tag) {
  asm volatile("{\n.reg .b128 t;\n.reg .b64 a, b;\nmov.b64 a, {%1, %2};\nmov.b64 b, {%3, %4};\nmov.b128 t, {a, b};\nst.relaxed.gpu.global.b128 [%0], t;\n}\n"
               ::"l"(p), "r"((__float_as_uint(a) & ~1u) | tag), "f"(b), "f"(c), "f"(d) : "memory");
}
__device__ __forceinline__ uint32_t stale8(const uint4 (&f)[8], uint32_t tag) {
  uint32_t r[4];
#pragma unroll
  for (int i = 0; i < 4; i++) asm("lop3.b32 %0, %1, %2, %3, 0x7E;" : "=r"(r[i]) : "r"(f[2 * i].x), "r"(f[2 * i + 1].x), "r"(tag));
  asm("lop3.b32 %0, %0, %1, %2, 0xFE;" : "+r"(r[0]) : "r"(r[1]), "r"(r[2]));
  return r[0] | r[3];
}

struct ConvC { uint32_t a1[2][4], wa[2], wb[2], sg; };
__device__ __forceinline__ uint64_t dsc(uint32_t lo, uint32_t hi) { return ((uint64_t)hi << 32) | lo; }
__device__ __forceinline__ uint32_t hfma(uint32_t a, uint32_t b, uint32_t c) { uint32_t r; asm("fma.rn.f16x2 %0, %1, %2, %3;" : "=r"(r) : "r"(a), "r"(b), "r"(c)); return r; }
__device__ __forceinline__ uint32_t hfnma(uint32_t a, uint32_t b, uint32_t c) { uint32_t r; asm("{.reg .b32 n; neg.f16x2 n, %1; fma.rn.f16x2 %0, n, %2, %3;}" : "=r"(r) : "r"(a), "r"(b), "r"(c)); return r; }
__device__ __forceinline__ uint32_t hmul16(uint32_t a, uint32_t b) { uint32_t r; asm("mul.rn.f16x2 %0, %1, %2;" : "=r"(r) : "r"(a), "r"(b)); return r; }
template <int N> __device__ __forceinline__ void keepu(uint32_t (&d)[N]) {
#pragma unroll
  for (int i = 0; i < N; i++) asm volatile("" : "+r"(d[i])::"memory");
}
__device__ __forceinline__ void conv_m1(const ConvC& K, uint32_t (&u)[16], uint32_t l) {
  wg_fence();
  wgmma_hrs_n64<1>(u, K.a1[0][0], K.a1[0][1], K.a1[0][2], K.a1[0][3], dsc(l, 32), 0);
  wgmma_hrs_n64<1>(u, K.a1[1][0], K.a1[1][1], K.a1[1][2], K.a1[1][3], dsc(l + 16, 32), 1);
  wg_commit();
}
__device__ __forceinline__ void conv_s2(const ConvC& K, uint32_t (&u)[16], uint32_t (&Z)[2][8], uint32_t dfl) {
  uint32_t fr[8], fi[8];
#pragma unroll
  for (int c = 0; c < 8; c++) {
    const uint32_t r = hfma(K.wa[c & 1], u[2 * c + 1], u[2 * c]);
    fi[c] = hfma(K.wb[c & 1], r, u[2 * c + 1]);
    fr[c] = hfma(K.wa[c & 1], fi[c], r);
  }
  wg_fence();
#pragma unroll
  for (int p = 0; p < 2; p++) {
    wgmma_hrs_n32<0>(Z[p], fr[4 * p], fr[4 * p + 2], fr[4 * p + 1], fr[4 * p + 3], dsc(dfl, 32), 0);
    wgmma_hrs_n32<0>(Z[p], fi[4 * p], fi[4 * p + 2], fi[4 * p + 1], fi[4 * p + 3], dsc(dfl + 16, 32), 1);
  }
  wg_commit();
}
__device__ __forceinline__ void conv_win(const ConvC& K, const uint32_t (&X)[2][8], uint32_t (&W)[2][8]) {
#pragma unroll
  for (int b = 0; b < 4; b++)
#pragma unroll
    for (int c = 0; c < 2; c++) {
      const uint32_t xr = X[b >> 1][2 * c + (b & 1)], xi = X[b >> 1][4 + 2 * c + (b & 1)];
      const int a = b ? b - 1 : 0;
      W[b >> 1][2 * c + (b & 1)] = b ? hfnma(K.sg, X[a >> 1][4 + 2 * c + (a & 1)], xr) : hmul16(xr, 0x3C003C00u);
      W[b >> 1][4 + 2 * c + (b & 1)] = b ? hfma(K.sg, X[a >> 1][2 * c + (a & 1)], xi) : hmul16(xi, 0x3C003C00u);
    }
}
template <int p>
__device__ __forceinline__ void conv_pw(uint32_t (&X)[2][8], uint32_t (&H)[2][8], uint32_t (&V)[8], uint32_t dil) {
  uint32_t pr[2][2], pi[2][2];
#pragma unroll
  for (int jj = 0; jj < 2; jj++)
#pragma unroll
    for (int c = 0; c < 2; c++) {
      const int j = 2 * p + jj;
      uint32_t sr = 0, si = 0;
#pragma unroll
      for (int a = 0; a <= j; a++) {
        const int b = j - a;
        const uint32_t hr = H[a >> 1][2 * c + (a & 1)], hi = H[a >> 1][4 + 2 * c + (a & 1)];
        const uint32_t xr = X[b >> 1][2 * c + (b & 1)], xi = X[b >> 1][4 + 2 * c + (b & 1)];
        sr = a == 0 ? hmul16(hr, xr) : hfma(hr, xr, sr);
        si = a == 0 ? hmul16(hr, xi) : hfma(hr, xi, si);
        sr = hfnma(hi, xi, sr);
        si = hfma(hi, xr, si);
      }
      pr[jj][c] = sr; pi[jj][c] = si;
    }
  wg_fence();
  wgmma_hrs_n32<0>(V, pr[0][0], pr[1][0], pr[0][1], pr[1][1], dsc(dil, 32), 0);
  wgmma_hrs_n32<0>(V, pi[0][0], pi[1][0], pi[0][1], pi[1][1], dsc(dil + 16, 32), 1);
  wg_commit();
}
template <int p>
__device__ __forceinline__ void conv_it(const ConvC& K, uint32_t (&V)[8], uint32_t vst) {
#pragma unroll
  for (int jj = 0; jj < 2; jj++) {
    uint32_t wr[2], wi[2];
#pragma unroll
    for (int c = 0; c < 2; c++) {
      const uint32_t r = hfnma(K.wa[c], V[4 + 2 * c + jj], V[2 * c + jj]);
      wi[c] = hfnma(K.wb[c], r, V[4 + 2 * c + jj]);
      wr[c] = hfnma(K.wa[c], wi[c], r);
    }
    stsm4(vst + (2 * p + jj) * 2048, wr[0], wr[1], wi[0], wi[1]);
  }
}
__device__ __forceinline__ void conv_m4(uint32_t (&y)[8], uint32_t (&a)[4][4], uint32_t d4l) {
  wg_fence();
  wgmma_hrs_n32<0>(y, a[0][0], a[0][1], a[0][2], a[0][3], dsc(d4l, 64), 0);
#pragma unroll
  for (int s = 1; s < 4; s++) wgmma_hrs_n32<0>(y, a[s][0], a[s][1], a[s][2], a[s][3], dsc(d4l + s * 16, 64), 1);
  wg_commit();
}

struct Params {
  CUtensorMap tmX0, tmW, tmX, tmWo, tmWo1, tmK, tmV, tmQ, tmOA, tmOB;
  const __nv_bfloat16 *shift_k, *h, *D, *x, *w, *wo, *q;
  float *part, *kv;
  uint4* o;
  const uint32_t *thr, *img;
};

__global__ void __cluster_dims__(2, 1, 1) __launch_bounds__(384, 1) fused_kernel(const __grid_constant__ Params P) {
  extern __shared__ __align__(1024) uint8_t smem[];
  const uint32_t sb = __shfl_sync(~0u, smem_u32(smem), 0);
  const uint32_t bars = sb + OFF_BAR;
  const int tid = threadIdx.x, lane = tid & 31;
  const int warp = __shfl_sync(~0u, tid >> 5, 0);
  const int rank = blockIdx.x & 1, cl = blockIdx.x >> 1;
  const unsigned c7 = cl + 6, g7 = (c7 * 37) >> 8;
  const int mb = cl < 4 ? 4 + cl : cl < 36 ? (cl - 4) >> 3 : g7 - 2;
  const int hq = cl < 4 ? 0 : cl < 36 ? (cl - 4) & 7 : 1 + c7 - 7 * g7;
  const int hp = 2 * hq + rank;
  const int rb = 2 * mb + (hq >> 2), cb = hq & 3;
#define BAR(i) (bars + 8 * (i))
#define OCNT(rb, hh) ((unsigned*)(P.o + (rb) * OBLK + 16 * 1024 + 8 * (hh)))
#define EPOCH (OCNT(rb, 2)[hp & 7])

  if (tid == 0) { STAMP(0, 0); GSTAMP(0, 30); }
  if (warp == 8) {
    if (elect_one()) {
      mbar_init(BAR(B_FULL1), 1);
      mbar_init(BAR(B_FIRST), 1);
      asm volatile("fence.mbarrier_init.release.cluster;" ::: "memory");
      mbar_expect(BAR(B_FIRST), STAGE_BYTES - 16384);
      tma2d(sb, &P.tmX0, 0, mb * 256, BAR(B_FIRST));
      tma2d(sb + 16384, &P.tmX0, 0, mb * 256 + 128, BAR(B_FIRST));
      tma3d(sb + 32768, &P.tmW, hp * 64, 0, 0, BAR(B_FIRST));
    }
    if (lane == 0) STAMP(3, 21);
  } else if (lane == 0) {
    const int wi = warp - (warp > 8);
#pragma unroll
    for (int r = 0; r < 6; r++)
      if (r < 5 || wi < B_COUNT - 56) mbar_init(BAR(1 + 11 * r + wi), ((uint32_t)(bar_counts(r) >> (4 * wi)) & 15) + 1);
    asm volatile("fence.mbarrier_init.release.cluster;" ::: "memory");
  }
  if (tid == 0) STAMP(2, 6);
  asm volatile("barrier.cluster.arrive.relaxed.aligned;\nbarrier.cluster.wait.aligned;" ::: "memory");
  if (warp == 8 && elect_one()) {
    mbar_expect(BAR(B_FULL1), 16384);
    tma2d_mc(sb + 8192 + rank * 16384, &P.tmX0, 0, mb * 256 + 64 + rank * 128, BAR(B_FULL1));
  }
  if (tid == 256) STAMP(2, 7);

  if (warp < 8) {
    asm volatile("setmaxnreg.inc.sync.aligned.u32 224;");
    const int wg = warp >> 2, w = warp & 3, g = lane >> 2, q = lane & 3, t = tid & 127;
    const bool elect = (t == 0);
    const uint32_t s16 = (sb & 0x3FFFF) >> 4;
    uint32_t pq[2][16], ux[16], uh[16], X[4][2][8], H[4][2][8];
    ConvC K;
    const uint32_t dfl = s16 + (OFF_F2F >> 4) + (8 << 16), dil = s16 + (OFF_F2I >> 4) + (8 << 16), d4l = s16 + (OFF_F4 >> 4) + (8 << 16);
    const uint32_t xl = s16 + (OFF_XT >> 4) + 4 * wg * (XT_STRIDE >> 4) + (8 << 16);
    const uint32_t hl = s16 + (OFF_H >> 4) + wg * 512 + (8 << 16);
    {
      float acc[2][96];
      if (SPLIT0) {
#pragma unroll
        for (int mt = 0; mt < 2; mt++) {
          mbar_wait(BAR(mt ? B_FULL1 : B_FIRST), 0);
          if (mt == 0 && elect) { STAMP(wg, 1); GSTAMP(wg, 26); }
          wg_fence();
#pragma unroll
          for (int ks = 0; ks < 4; ks++)
            wgmma_ss_n192<0, 1>(acc[mt], dsc(s16 + wg * 1024 + mt * 512 + (1 << 16) + ks * 2, SW128), dsc(s16 + 2048 + (512 << 16) + ks * 128, SW128), ks != 0);
        }
        wg_commit();
      }
      int st = SPLIT0 ? 1 : 0, ph = 0;
#pragma unroll 1
      for (int kb = SPLIT0 ? 1 : 0; kb < 14; kb++) {
        mbar_wait(BAR(B_FULL1 + st), ph);
        if (kb == 0 && elect) { STAMP(wg, 1); GSTAMP(wg, 26); }
        if (kb == 8 && elect) { STAMP(wg, 16); GSTAMP(wg, 25); }
        const uint32_t da = s16 + st * (STAGE_BYTES >> 4) + wg * 1024 + (1 << 16);
        const uint32_t db = s16 + st * (STAGE_BYTES >> 4) + 2048 + (512 << 16);
        wg_fence();
#pragma unroll
        for (int ks = 0; ks < 4; ks++) {
          wgmma_ss_n192<0, 1>(acc[0], dsc(da + ks * 2, SW128), dsc(db + ks * 128, SW128), (kb | ks) != 0);
          wgmma_ss_n192<0, 1>(acc[1], dsc(da + 512 + ks * 2, SW128), dsc(db + ks * 128, SW128), (kb | ks) != 0);
        }
        wg_commit();
        wg_wait<1>();
        if (kb > 0 && t < 2) mbar_arrive_cl(BAR(B_EMPTY1 + (st == 0 ? 2 : st - 1)), t);
        if (++st == 3) { st = 0; ph ^= 1; }
      }
#define TAIL_MMA(mt, stage) do { wg_fence(); _Pragma("unroll") for (int ks = 0; ks < 4; ks++) \
        wgmma_ss_n192<0, 1>(acc[mt], dsc(s16 + (stage) * (STAGE_BYTES >> 4) + wg * 1024 + (mt) * 512 + (1 << 16) + ks * 2, SW128), \
                            dsc(s16 + (stage) * (STAGE_BYTES >> 4) + 2048 + (512 << 16) + ks * 128, SW128), 1); wg_commit(); } while (0)
      mbar_wait(BAR(B_FULL1 + 2), 0);
      TAIL_MMA(0, 2);
      wg_wait<1>();
      if (elect) mbar_arrive(BAR(B_SFREE));
      mbar_wait(BAR(B_FULL1 + 0), 1);
      TAIL_MMA(0, 0);
      TAIL_MMA(1, 2);
      const uint32_t lrow = sb + wg * 16384 + (16 * w + 8 * ((lane >> 3) & 1) + (lane & 7)) * 128 + (((lane >> 4) ^ (lane & 7)) << 4);
#define E1K(mt, i) do { if (opaque_true()) { _Pragma("unroll") for (int j = (i); j < (i) + 2; j++) { \
          const float* a = &acc[mt][32 + 8 * j]; const float* b = a + 32; const uint32_t o = (lrow ^ (j * 32)) + (mt) * 8192; \
          stsm4(o + 2 * STAGE_BYTES, pk2(b[0], b[1]), pk2(b[2], b[3]), pk2(b[4], b[5]), pk2(b[6], b[7])); \
          stsm4(o, phi2(a[0], a[1]), phi2(a[2], a[3]), phi2(a[4], a[5]), phi2(a[6], a[7])); } } } while (0)
#define E1Q(mt) do { if (opaque_true()) { _Pragma("unroll") for (int i = 0; i < 16; i++) pq[mt][i] = phi2(acc[mt][2 * i], acc[mt][2 * i + 1]); } } while (0)
#define LOAD_K() do { const uint4* ct = (const uint4*)P.thr + t; \
        _Pragma("unroll") for (int s = 0; s < 2; s++) { const uint4 u = ld_na4(ct + s * 128); K.a1[s][0] = u.x; K.a1[s][1] = u.y; K.a1[s][2] = u.z; K.a1[s][3] = u.w; } \
        const uint4 u = ld_na4(ct + 2 * 128); K.wa[0] = u.x; K.wa[1] = u.y; K.wb[0] = u.z; K.wb[1] = u.w; \
        K.sg = (lane & 4) ? 0xBC00BC00u : 0x3C003C00u; } while (0)
#define PK_READY(mt) do { fence_async(); __syncwarp(); if (lane == 0) mbar_arrive(BAR(B_PKRDY + (mt))); } while (0)
      wg_wait<1>();
      keep(acc[0]);
      if (elect) STAMP(wg, 18);
      E1K(0, 0);
      TAIL_MMA(1, 0);
      E1K(0, 2);
      if (elect) STAMP(wg, 19);
      PK_READY(0);
      wg_wait<0>();
      keep(acc[1]);
      if (elect) mbar_arrive(BAR(B_G1DONE));
      asm volatile("setmaxnreg.dec.sync.aligned.u32 200;");
      if (elect) { STAMP(wg, 2); GSTAMP(wg, 27); }
      E1K(1, 0);
      if (elect) STAMP(wg, 20);
      E1K(1, 2);
      if (elect) STAMP(wg, 21);
      PK_READY(1);
      if (elect) STAMP(wg, 3);
      LOAD_K();
      if (elect) STAMP(wg, 4);
      E1Q(0);
      E1Q(1);
      if (elect) STAMP(wg, 17);
      mbar_wait(BAR(B_H), 0);
      conv_m1(K, ux, xl);
      conv_m1(K, uh, hl);
      wg_wait<1>(); keepu(ux);
      if (lane == 0) mbar_arrive_cl(BAR(B_XFREE + 4 * wg), rank ^ 1);
      conv_s2(K, ux, X[0], dfl);
      wg_wait<1>(); keepu(uh);
      conv_s2(K, uh, H[0], dfl);
    }
    if (elect) STAMP(wg, 5);
    {
      uint32_t vst = sb + wg * 8192 + w * 512 + lane * 16, vld = sb + wg * 8192 + w * 2048 + lane * 16;
      uint32_t ya = mapa(sb + OFF_XT + 4 * wg * XT_STRIDE + (2 * rank + (w & 1)) * 1024 + lane * 16, w >> 1);
      const uint32_t ybar = mapa(BAR(B_Y), w >> 1);
      asm volatile("" : "+r"(vst), "+r"(vld), "+r"(ya));
      uint32_t W[2][8], V0[8], V1[8], y[8], a[4][4];
      uint4 ov[4];
      uint4* const ot = P.o + (2 * mb + wg) * OBLK + hq * 1024 + (16 * w + g) * 8 + ((4 * rank + q) ^ g);
#define YOUT(i) do { if ((w >> 1) == rank) { \
          asm volatile("st.shared.v4.b32 [%0], {%1,%2,%3,%4};" ::"r"(ya + (i) * XT_STRIDE), "r"(y[0]), "r"(y[2]), "r"(y[4]), "r"(y[6]) : "memory"); \
          asm volatile("st.shared.v4.b32 [%0], {%1,%2,%3,%4};" ::"r"(ya + (i) * XT_STRIDE + 512), "r"(y[1]), "r"(y[3]), "r"(y[5]), "r"(y[7]) : "memory"); \
        } else { \
          mbar_wait(BAR(B_XFREE + 4 * wg + (i)), 0); \
          st_async4(ya + (i) * XT_STRIDE, y[0], y[2], y[4], y[6], ybar); \
          st_async4(ya + (i) * XT_STRIDE + 512, y[1], y[3], y[5], y[7], ybar); } } while (0)
      auto ocalc = [&](const int hh) {
        if (hh == 0) {
          if (elect) STAMP(wg, 8);
          mbar_wait(BAR(B_KV), 0);
          if (elect) STAMP(wg, 9);
        } else mbar_wait(BAR(B_KV1), 0);
        float oa[2][20];
        wg_fence();
#pragma unroll
        for (int m = 0; m < 4; m++) {
          const uint32_t* p = &pq[m & 1][8 * hh + 4 * (m >> 1)];
          wgmma_rs_n40<1>(oa[m & 1], p[0], p[1], p[2], p[3], dsc(s16 + (OFF_KVB >> 4) + hh * 160 + (m >> 1) * 16 + (8 << 16), 32), m >> 1);
        }
        wg_commit();
        wg_wait<0>();
#pragma unroll
        for (int mt = 0; mt < 2; mt++) {
          float (&o)[20] = oa[mt];
          keep(o);
          const uint32_t den = hadd(pk2(o[16], o[18]), 0x35863586u);
#pragma unroll
          for (int r = 0; r < 2; r++) {
            const float ri = rcp_fast(__uint_as_float(r ? (den & 0xFFFF0000u) : (den << 16)));
            uint4 u;
            u.x = pk2(o[2 * r] * ri, o[2 * r + 1] * ri);
            u.y = pk2(o[4 + 2 * r] * ri, o[5 + 2 * r] * ri);
            u.z = pk2(o[8 + 2 * r] * ri, o[9 + 2 * r] * ri);
            u.w = pk2(o[12 + 2 * r] * ri, o[13 + 2 * r] * ri);
            if (hh == 0) st_cg4(ot + (64 * mt + 8 * r) * 8, u); else ov[2 * mt + r] = u;
          }
        }
        if (hh == 0) {
          __syncwarp();
          if (lane == 0) mbar_arrive(BAR(B_ODONE));
          if (elect) STAMP(wg, 10);
        }
      };
      auto trickle = [&](const int qs) {
        const int m = qs - 2 * (OCH + O1D) - (TRICK - 1);
        if (m >= 0 && m < 4) {
          st_cg4(ot + 8 * 1024 + (64 * (m >> 1) + 8 * (m & 1)) * 8, ov[m]);
          if (m == 3) { __syncwarp(); if (lane == 0) mbar_arrive(BAR(B_ODONE1)); }
        }
      };
#pragma unroll
      for (int i = 0; i < 4; i++) {
        const bool nx = i < 3;
        const int n = nx ? i + 1 : i;
        const uint32_t vo = (i & 1) ? OFF_H + (i >> 1) * 16384 : OFF_VP;
        if (2 * i == OCH) ocalc(0);
        if (2 * i == OCH + O1D) ocalc(1);
        if (nx) {
          conv_m1(K, ux, xl + n * (XT_STRIDE >> 4));
          conv_m1(K, uh, hl + (n >> 1) * 1024 + (n & 1) * 256);
        }
        if (2 * i != OCH && 2 * i != OCH + O1D) { if (nx) { if (i > 0) wg_wait<3>(); else wg_wait<2>(); } else wg_wait<1>(); }
        keepu(X[i][0]); keepu(X[i][1]); keepu(H[i][0]); keepu(H[i][1]);
        conv_win(K, X[i], W);
        trickle(4 * i);
        conv_pw<0>(W, H[i], V0, dil);
        conv_pw<1>(W, H[i], V1, dil);
        trickle(4 * i + 1);
        wg_wait<2>();
        if (i > 0) { keepu(y); YOUT(i - 1); }
        if (2 * i + 1 == OCH) ocalc(0);
        if (2 * i + 1 == OCH + O1D) ocalc(1);
        if (nx) {
          keepu(ux); keepu(uh);
          if (lane == 0) mbar_arrive_cl(BAR(B_XFREE + 4 * wg + n), rank ^ 1);
          conv_s2(K, ux, X[n], dfl);
          wg_wait<1>();
        } else wg_wait<0>();
        keepu(V0); keepu(V1);
        trickle(4 * i + 2);
        if (i == 0) mbar_wait(BAR(B_H2), 0);
        conv_it<0>(K, V0, vst + vo);
        conv_it<1>(K, V1, vst + vo);
        bar_sync(1 + wg);
#pragma unroll
        for (int s = 0; s < 4; s++) ldsm4t(a[s], vld + vo + s * 512);
        if (nx) conv_s2(K, uh, H[n], dfl);
        conv_m4(y, a, d4l);
        trickle(4 * i + 3);
        if (i > 0 && lane < 2) mbar_arrive_cl(BAR(B_AFREE + i - 1), lane);
        if (elect && i < 3) STAMP(wg, i < 2 ? 6 + i : 9 + i);
      }
      wg_wait<0>(); keepu(y);
      YOUT(3);
      __syncwarp();
      if (lane == 0) mbar_arrive(BAR(B_Y));
      if (elect) STAMP(wg, 12);
    }
    {
      float acc[64];
#define G2_MMA(da, db, first) do { wg_fence(); _Pragma("unroll") for (int ks = 0; ks < 4; ks++) \
        wgmma_ss_n128<0, 1>(acc, dsc((da) + ks * 2, SW128), dsc((db) + ks * 128, SW128), ks || !(first)); wg_commit(); } while (0)
      const uint32_t a0 = s16 + wg * 512 + (1 << 16), b0 = s16 + (512 << 16);
      uint64_t ta = SLOT_A, tb = SLOT_B;
      uint32_t da = a0 + (SLOT_A & 15) * 1024, db = b0 + (SLOT_B & 15) * 1024, fb = BAR(B_FULL2);
      uint32_t cons = mapa(BAR(B_CONS2 - 1), t & 1);
      const bool rel = __shfl_sync(~0u, t, lane) < 2;
#pragma unroll 1
      for (int kb = 0; kb < HOLD2; kb++) {
        mbar_wait(fb, 0);
        if (kb == 0 && elect) { STAMP(wg, 13); GSTAMP(wg, 28); }
        G2_MMA(da, db, kb == 0);
        ta >>= 4; tb >>= 4;
        da = a0 + ((uint32_t)ta & 15) * 1024; db = b0 + ((uint32_t)tb & 15) * 1024; fb += 8;
        asm volatile("" : "+r"(da), "+r"(db));
        wg_wait<1>();
        if (kb > 0 && kb < 12 && rel) asm volatile("mbarrier.arrive.shared::cluster.b64 _, [%0];" ::"r"(cons) : "memory");
        cons += 8;
      }
#pragma unroll
      for (int kb = HOLD2; kb < 16; kb++) {
        if (wg == 1) mbar_wait(BAR(B_FULL2 + kb), 0);
        else if (kb == HOLD2) asm volatile("bar.sync 3, 256;" ::: "memory");
        G2_MMA(a0 + ((SLOT_A >> (4 * kb)) & 15) * 1024, b0 + ((SLOT_B >> (4 * kb)) & 15) * 1024, false);
      }
      if (wg == 1) asm volatile("bar.arrive 3, 256;" ::: "memory");
      const uint32_t stg = sb + wg * 8192 + w * 2048, so0 = ((SLOT_A >> 56) & 15) * 16384, so1 = ((SLOT_A >> 60) & 15) * 16384;
      const uint32_t lrow = stg + (8 * ((lane >> 3) & 1) + (lane & 7)) * 128 + (((lane >> 4) ^ (lane & 7)) << 4);
      const int col = 1024 + 256 * cb + 128 * rank, row = 128 * rb + 64 * wg + 16 * w;
      wg_wait<0>();
      keep(acc);
      if (elect) { STAMP(wg, 14); GSTAMP(wg, 29); }
#pragma unroll
      for (int cp = 0; cp < 8; cp++) {
        const float* a = &acc[8 * cp];
        stsm4((lrow ^ ((cp & 3) * 32)) + (cp >> 2 ? so1 : so0), pk2(a[0], a[1]), pk2(a[2], a[3]), pk2(a[4], a[5]), pk2(a[6], a[7]));
        if ((cp & 3) == 3) {
          fence_async();
          __syncwarp();
          if (elect_one()) tma2d_st(&P.tmOB, stg + (cp >> 2 ? so1 : so0), col + (cp >> 2) * 64, row);
        }
      }
      asm volatile("cp.async.bulk.commit_group;\ncp.async.bulk.wait_group.read 0;" ::: "memory");
      if (elect) {
        STAMP(wg, 15); GSTAMP(wg, 31); PDUMP(wg); if (wg == 0) PDUMP(2);
      }
    }
  } else {
    asm volatile("setmaxnreg.dec.sync.aligned.u32 56;");
    const int hw = warp - 9, g = lane >> 2, q = lane & 3;
#define sbar (bars + 8 * (B_STG - 18) + 16 * warp)
    if (warp == 8) {
      if (D1) __nanosleep(D1);
      int st = 1, pp = 1;
      const uint8_t* pfx = (const uint8_t*)P.x + (mb * 256 + hp * 16 + (lane & 15)) * 2048;
      const uint8_t* pfw = (const uint8_t*)P.w + (mb * 8 + (lane & 7)) * 6144 + (lane >> 3) * 2048 + hp * 128;
#pragma unroll 1
      for (int kb = 1; kb < 16; kb++) {
        if (kb >= 3) mbar_wait(BAR(B_EMPTY1 + st), pp);
        const uint32_t sa = sb + st * STAGE_BYTES;
        if (elect_one()) {
          mbar_expect(BAR(B_FULL1 + st), STAGE_BYTES);
          tma2d_mc(sa + rank * 16384, &P.tmX, kb * 64, mb * 256 + rank * 128, BAR(B_FULL1 + st));
          tma3d(sa + 32768, &P.tmW, hp * 64, kb * 64, 0, BAR(B_FULL1 + st));
        }
        if (kb == 1 && lane == 0) STAMP(2, 24);
        if (PFD && kb >= 2) {
#pragma unroll 1
          for (int j = kb == 2 ? 3 : kb + PFD; j <= kb + PFD && j < 16; j++) {
            if (lane < 16) asm volatile("prefetch.global.L2 [%0];" ::"l"(pfx + j * 128));
            if (lane < 24) asm volatile("prefetch.global.L2 [%0];" ::"l"(pfw + j * (64 * 6144)));
          }
          if (kb >= QPF && kb < QPF + 8) asm volatile("prefetch.global.L2 [%0];" ::"l"((const uint8_t*)P.q + (blockIdx.x * 256 + (kb - QPF) * 32 + lane) * 128));
          if (kb >= 4)
            asm volatile("prefetch.global.L2 [%0];" ::"l"(kb < 12 ? (const uint8_t*)P.h + ((2 * cl + rank) * 256 + (kb - 4) * 32 + lane) * 128
                                                                  : (const uint8_t*)P.wo + (blockIdx.x * 128 + (kb - 12) * 32 + lane) * 128));
        }
        if (++st == 3) { st = 0; pp ^= 1; }
      }
      if (lane == 0) STAMP(2, 1);
    } else {
      {
        const uint32_t clk0 = __shfl_sync(~0u, (uint32_t)clock(), 0), stg = sb + OFF_STG + hw * STG_STRIDE;
        const unsigned epoch = __shfl_sync(~0u, EPOCH, 0);
        const uint32_t tag = ~epoch & 1;
        uint32_t tap[2][4];
#pragma unroll
        for (int cg = 0; cg < 2; cg++) {
          const uint2 u = __ldg((const uint2*)(P.shift_k + (16 * cl + 8 * cg + g) * 4));
          tap[cg][0] = __byte_perm(u.x, 0, 0x1010); tap[cg][1] = __byte_perm(u.x, 0, 0x3232);
          tap[cg][2] = __byte_perm(u.y, 0, 0x1010); tap[cg][3] = __byte_perm(u.y, 0, 0x3232);
        }
        if (hw == 0 && lane < 8) *(float*)(smem + OFF_D + 4 * lane) = __bfloat162float(P.D[16 * cl + 8 * rank + lane]);
        if (hw == 1 && lane < 24) asm volatile("prefetch.global.L2 [%0];" ::"l"(P.thr + (lane + 24 * rank) * 32));
        if (hw == 0 && elect_one()) {
          *(volatile unsigned*)(smem + OFF_EPOCH) = epoch;
          mbar_expect(BAR(B_XRAW), 16384);
          mbar_expect(BAR(B_Y), 16384 + 64);
        }
        for (int i = hw * 32 + lane; i < 528; i += 96) st_tag4(P.part + (hp * 8 + mb) * 2176 + 4 * i, 0.f, 0.f, 0.f, 0.f, tag ^ 1);
        if (hw < 2 || lane < 2) st_tag4(P.kv + hp * 2176 + (4 * (hw < 2 ? 64 * mb + 32 * hw + lane : 512 + 8 * (mb & 1) + (mb & 6) + lane)), 0.f, 0.f, 0.f, 0.f, tag ^ 1);
        if (lane == 0) STAMP(3, hw);
        const uint32_t xo = sb + OFF_XT + g * XT_STRIDE + rank * 2048 + q * 4;
        const int krow = 8 + (lane & 7) - (lane >> 3);
        const uint32_t ka = stg + krow * 32 + ((krow & 4) << 2), va = stg + 2304 + lane * 32 + ((lane & 4) << 2);
        int ph = 0, b = 0;
#pragma unroll 1
        for (int ci = hw - 3; ci < 16; ci += 3) {
          const uint32_t bo = b ? OFF_F2F - OFF_STG : 0, bn = b ? 0 : OFF_F2F - OFF_STG;
          if (ci + 3 < 16) {
            while (__any_sync(~0u, (uint32_t)clock() - clk0 < HSTART + (ci + 3) * PACE)) __nanosleep(64);
            if (elect_one()) {
              mbar_expect(sbar + 8 * (b ^ 1), 2304 + 2048);
              tma2d(stg + bn, &P.tmK, 16 * cl, 1024 * rank + 64 * (ci + 3) - 8, sbar + 8 * (b ^ 1));
              tma2d(stg + bn + 2304, &P.tmV, 16 * cl, 1024 * rank + 64 * (ci + 3), sbar + 8 * (b ^ 1));
            }
          }
          if (ci >= 0) {
            mbar_wait(sbar + 8 * b, (ph >> b) & 1);
            ph ^= 1 << b;
#pragma unroll 1
            for (int grp = 0; grp < 2; grp++) {
#pragma unroll
              for (int cg = 0; cg < 2; cg++) {
                const uint32_t dst = mapa(xo + (ci >> 3) * 1024 + ((ci & 7) * 4 + 2 * grp) * 16, cg), xbar = mapa(BAR(B_XRAW), cg);
                uint32_t vv[4], kk[4][4];
                ldsm4t(vv, (va ^ (cg * 16)) + bo + grp * 1024);
#pragma unroll
                for (int rg = 0; rg < 4; rg++) ldsm4t(kk[rg], (ka ^ (cg * 16)) + bo + grp * 1024 + rg * 256);
#pragma unroll
                for (int rg = 0; rg < 4; rg++)
                  vv[rg] = hmul(hadd(hadd(hadd(hmul(kk[rg][3], tap[cg][3]), hmul(kk[rg][2], tap[cg][2])), hmul(kk[rg][1], tap[cg][1])), hmul(kk[rg][0], tap[cg][0])), vv[rg]);
                if (cg == rank) {
#pragma unroll
                  for (int rg = 0; rg < 4; rg++) asm volatile("st.shared.b32 [%0], %1;" ::"r"(dst + (rg & 1) * 512 + (rg >> 1) * 16), "r"(vv[rg]) : "memory");
                } else {
#pragma unroll
                  for (int rg = 0; rg < 4; rg++) st_async(dst + (rg & 1) * 512 + (rg >> 1) * 16, vv[rg], xbar);
                }
              }
            }
          }
          b ^= 1;
        }
      }
      if (lane == 0) STAMP(3, 3 + hw);
      asm volatile("bar.sync 4, 96;" ::: "memory");
      if (hw == 0 && elect_one()) { mbar_expect(BAR(B_XT), 10240); bulk_ld(sb + OFF_F2F, P.img, 10240, BAR(B_XT)); }
      mbar_wait(BAR(B_XRAW), 0);
    }
    int e1 = 0;
#pragma unroll 1
    for (int n = hw < 0 ? 3 : 0; n < 4; n++) {
      const bool isH = n >= 3;
      const int c = isH ? (warp & 1) + 2 * (warp & 2) : hw + 3 * n;
      if (c < 8) {
        int ln;
        asm volatile("mov.u32 %0, %%laneid;" : "=r"(ln));
        uint8_t* dst = smem + (isH ? OFF_H + (c & 2) * 8192 + (c >> 2) * 8192 + (c & 1) * 4096 : OFF_XT + c * XT_STRIDE) + ((ln >> 4) * 512 + (ln & 15) * 16);
        const uint8_t* src0 = isH ? (const uint8_t*)P.h + (16 * cl + 8 * rank + c) * 4096 + ((ln & 15) * 32 + (ln & 16)) : dst;
        const uint8_t* src1 = src0 + (isH ? 512 : 256);
        uint32_t v[32];
#pragma unroll
        for (int i = 0; i < 8; i++) {
          const uint4 u = *(const uint4*)(((i & 1) ? src1 : src0) + (i >> 1) * 1024);
          v[4 * i] = u.x; v[4 * i + 1] = u.y; v[4 * i + 2] = u.z; v[4 * i + 3] = u.w;
        }
        if (isH) mbar_wait(BAR(B_XT), 0);
        const float f0 = __uint_as_float(v[0] << 16) + ((isH && ln == 0) ? *(const float*)(smem + OFF_D + 4 * c) : 0.f);
        const int e = norm_exp(v, f0);
        norm_cvt(v, f0, e);
        if (isH) mbar_wait(BAR(B_SFREE), 0);
        else if (ln == 0) smem[OFF_EX + c] = e;
        e1 = e;
#pragma unroll
        for (int i = 0; i < 8; i++)
          *(uint4*)(dst + (i >> 1) * 1024 + (i & 1) * 256) = make_uint4(v[4 * i], v[4 * i + 1], v[4 * i + 2], v[4 * i + 3]);
        if (n < 2 && elect_one()) {
          if (n == 0) mbar_expect(sbar, 4096);
          tma3d(sb + OFF_STG + 2048 * c, &P.tmQ, 16 * cl, 64 * rank, 2 * c, sbar);
        }
      }
      if (n >= 2) {
        fence_async();
        __syncwarp();
        if (lane == 0) { mbar_arrive(BAR(isH ? B_H : B_XT)); STAMP(3, (isH ? 17 : 13) + hw); }
      }
    }
#define SLOT(tab, kb) (sb + ((uint32_t)((tab) >> (4 * (kb))) & 15) * 16384)
#define LOAD_B(kb) tma4d(SLOT(SLOT_B, kb), &P.tmWo, 0, ((kb) >> 3) * 32, 2 * ((kb) & 7), 4 * cb + 2 * rank, BAR(B_FULL2 + (kb)))
#define LOAD_A(kb) bulk_ld_mc(SLOT(SLOT_A, kb) + rank * 8192, P.o + rb * OBLK + (kb) * 1024 + rank * 512, 8192, BAR(B_FULL2 + (kb)))
    asm volatile("setmaxnreg.inc.sync.aligned.u32 104;");
    {
    int tid;
    asm volatile("mov.u32 %0, %%tid.x;" : "=r"(tid));
    const int lane = tid & 31, g = lane >> 2, q = lane & 3;
    const unsigned epoch = *(volatile unsigned*)(smem + OFF_EPOCH);
    const uint32_t tag = ~epoch & 1;
    const int pi = hw < 2 ? 64 * mb - 288 + tid : 512 + 8 * (mb & 1) + (mb & 6) + (lane & 1);
    const float* psrc = P.part + hp * 8 * 2176 + 4 * pi;
    uint4 f[8];
    {
      const uint32_t s16 = (sb & 0x3FFFF) >> 4;
      const int t = tid & 127, c = 2 + (warp & 1) + 2 * (warp & 2);
      const uint4* hp4 = (const uint4*)(P.h + (16 * cl + 8 * rank + c) * 2048) + ((lane & 15) * 2 + (lane >> 4));
      uint32_t v[32];
#pragma unroll
      for (int i = 0; i < 8; i++) { const uint4 u = ld_na4(hp4 + i * 32); v[4 * i] = u.x; v[4 * i + 1] = u.y; v[4 * i + 2] = u.z; v[4 * i + 3] = u.w; }
      float kva[36];
#pragma unroll
      for (int mt = 0; mt < 2; mt++) {
        mbar_wait(BAR(B_PKRDY + mt), 0);
        wg_fence();
#pragma unroll
        for (int ks = 0; ks < 8; ks++) {
          const uint32_t o = (ks >> 2) * 1024 + mt * 512 + (ks & 3) * 128, vb = (2 * STAGE_BYTES >> 4) + o;
          wgmma_ss_n72<1, 1>(kva, dsc(s16 + o + (1 << 16), SW128), dsc(s16 + vb + (((OFF_ONES >> 4) - vb) << 16), SW128), (mt | ks) != 0);
        }
        wg_commit();
        if (mt == 0 && hw < 0) {
          mbar_wait(BAR(B_G1DONE), 0);
          if (elect_one()) {
#pragma unroll
            for (int kb = 0; kb < BEARLY; kb++) { mbar_expect(BAR(B_FULL2 + kb), 16384); LOAD_B(kb); }
          }
        }
      }
      float* pdst = P.part + (hp * 8 + mb) * 2176 + t * 4;
      float* zdst = P.part + (hp * 8 + mb) * 2176 + 2048 + (t >> 1);
      asm volatile("" : "+l"(pdst), "+l"(zdst));
      wg_wait<0>();
      keep(kva);
      if (hw < 1) {
#pragma unroll
        for (int c = 0; c < 4; c++) st_tag4(pdst + c * 512, kva[4 * c], kva[4 * c + 1], kva[4 * c + 2], kva[4 * c + 3], tag);
      } else {
#pragma unroll
        for (int c = 4; c < 8; c++) st_tag4(pdst + (c - 4) * 512, kva[4 * c], kva[4 * c + 1], kva[4 * c + 2], kva[4 * c + 3], tag);
      }
      const float z2 = __shfl_down_sync(~0u, kva[32], 4), z3 = __shfl_down_sync(~0u, kva[34], 4);
      if (!(lane & 7)) st_tag4(zdst, kva[32], kva[34], z2, z3, tag);
      if (lane == 0) mbar_arrive(BAR(B_PKFREE));
      const uint32_t cst = clock();
      if (hw == 0 && lane == 0) STAMP(3, 24);
      const float f0 = __uint_as_float(v[0] << 16) + (lane == 0 ? *(const float*)(smem + OFF_D + 4 * c) : 0.f);
      const int e = norm_exp(v, f0);
      norm_cvt(v, f0, e);
      if (hw >= 0) {
        while (__any_sync(~0u, (uint32_t)clock() - cst < PD1)) __nanosleep(20);
        if (hw == 0 && lane == 0) STAMP(3, 20);
#pragma unroll
        for (int p = 0; p < 8; p++) f[p] = ld_rlx4(psrc + p * 2176);
      }
      uint8_t* dst = smem + OFF_H + 16384 + (warp & 3) * 4096 + (lane >> 4) * 512 + (lane & 15) * 16;
#pragma unroll
      for (int i = 0; i < 8; i++)
        *(uint4*)(dst + (i >> 1) * 1024 + (i & 1) * 256) = make_uint4(v[4 * i], v[4 * i + 1], v[4 * i + 2], v[4 * i + 3]);
      if (lane < 4) {
        const int cc = c - (lane & 2);
        st_async(mapa(sb + OFF_SCALE + (8 * rank + cc) * 4, lane & 1), min(max(((lane & 2) ? e1 : e) + smem[OFF_EX + cc] - 124, 1), 254) << 23, mapa(BAR(B_Y), lane & 1));
      }
    }
#define H2_READY() do { fence_async(); __syncwarp(); if (lane == 0) mbar_arrive(BAR(B_H2)); } while (0)
    if (warp == 8) {
      H2_READY();
      mbar_wait(BAR(B_PKFREE), 0);
      {
        const uint32_t c0 = clock();
#pragma unroll 1
        for (int i = 0; i < 2 * NPRE - 2 * BEARLY; i++) {
          const int kb = (i >> 1) + BEARLY;
          while (__any_sync(~0u, (uint32_t)clock() - c0 < i * BPACE)) __nanosleep(32);
          if (elect_one()) {
            if (!(i & 1)) mbar_expect(BAR(B_FULL2 + kb), 16384);
            tma4d(SLOT(SLOT_B, kb) + (i & 1) * 8192, &P.tmWo1, 0, 0, 2 * kb, 4 * cb + 2 * rank + (i & 1), BAR(B_FULL2 + kb));
            if (i == 0) mbar_expect(BAR(B_Q), 8192);
            if (i < 4) tma3d(sb + OFF_SPARE + 2048 * i, &P.tmQ, 16 * cl, 64 * rank + 32 * (i >> 1), 2 * ((i + 6) & 7), BAR(B_Q));
          }
        }
      }
      if (lane == 0) STAMP(2, 2);
      mbar_wait(BAR(B_AFREE), 0);
      if (elect_one()) mbar_expect(BAR(B_FULL2), 16384);
      {
        const uint32_t dst = SLOT(SLOT_A, 0) + rank * 8192;
        const uint4* src = P.o + rb * OBLK + rank * 512;
        poll_ge(OCNT(rb, 0), 16 * (epoch + 1));
        asm volatile("fence.proxy.async.global;" ::: "memory");
        if (lane == 0) STAMP(2, 3);
        if (elect_one()) bulk_ld_mc(dst, src, 8192, BAR(B_FULL2));
        if (lane == 0) STAMP(3, 23);
      }
#pragma unroll 1
      for (int kb = 1; kb < NPRE; kb++) {
        mbar_wait(BAR(kb < 4 ? B_AFREE + kb - 1 : B_CONS2), 0);
        if (elect_one()) { mbar_expect(BAR(B_FULL2 + kb), 16384); LOAD_A(kb); }
      }
#pragma unroll 1
      for (int kb = NPRE; kb < 16; kb++) {
        mbar_wait(BAR(B_CONS2 + kb - 5), 0);
        if (kb == 8) mbar_wait(BAR(B_O1RDY), 0);
        if (elect_one()) { mbar_expect(BAR(B_FULL2 + kb), 32768); LOAD_A(kb); LOAD_B(kb); }
      }
      if (lane == 0) { EPOCH = epoch + 1; STAMP(2, 5); }
    } else {
      {
#pragma unroll 1
        for (int n = 0; __any_sync(~0u, stale8(f, tag) & 1); n++) {
#pragma unroll
          for (int p = 0; p < 8; p++) ld_stale4(f[p], psrc + p * 2176, tag);
          if (n > SPIN_LIMIT) __trap();
        }
        float s0 = 0.f, s1 = 0.f, s2 = 0.f, s3 = 0.f;
#pragma unroll
        for (int p = 0; p < 8; p++) { s0 += __uint_as_float(f[p].x); s1 += __uint_as_float(f[p].y); s2 += __uint_as_float(f[p].z); s3 += __uint_as_float(f[p].w); }
        if (hw < 2 || lane < 2) st_tag4(P.kv + hp * 2176 + (4 * pi), s0, s1, s2, s3, tag);
      }
      const uint32_t cs2 = clock();
      if (lane == 0 && hw == 0) STAMP(3, 8);
      H2_READY();
      if (hw == 2) {
        unsigned* cnt = OCNT(2 * mb + lane, 0);
#pragma unroll 1
        for (int hh = 0; hh < 2; hh++) {
          mbar_wait(BAR(hh ? B_ODONE1 : B_ODONE), 0);
          if (lane < 2) asm volatile("red.release.gpu.global.add.u32 [%0], 1;" ::"l"(cnt) : "memory");
          cnt += 32;
          if (lane == 0) STAMP(3, hh ? 6 : 7);
        }
        poll_ge(OCNT(rb, 1), 16 * (epoch + 1));
        asm volatile("fence.proxy.async.global;" ::: "memory");
        if (lane == 0) { mbar_arrive(BAR(B_O1RDY)); STAMP(2, 4); }
        __syncwarp();
      } else {
        const int t = tid - 288;
        const float* src = P.kv + hp * 2176 + 4 * (t + 32 * hw);
        const float* zsrc = P.kv + hp * 2176 + (2048 + (t & 48) + 2 * (lane & 6));
        mbar_wait(BAR(B_PKFREE), 0);
        while (__any_sync(~0u, (uint32_t)clock() - cs2 < PD2)) __nanosleep(20);
        uint4 zp = ld_rlx4(zsrc);
#pragma unroll
        for (int p = 0; p < 8; p++) f[p] = ld_rlx4(src + 4 * ((p & 3) * 128 + (p >> 2) * 32));
        if (!opaque_true()) __trap();
#pragma unroll 1
        for (int n = 0; __any_sync(~0u, (stale8(f, tag) | (zp.x ^ tag)) & 1); n++) {
          ld_stale4(zp, zsrc, tag);
#pragma unroll
          for (int p = 0; p < 8; p++) ld_stale4(f[p], src + 4 * ((p & 3) * 128 + (p >> 2) * 32), tag);
          if (n > SPIN_LIMIT) __trap();
        }
#define PK2U(a, b) pk2(__uint_as_float(a), __uint_as_float(b))
        const uint32_t zf = (lane & 1) ? ((lane & 8) ? zp.w : zp.z) : ((lane & 8) ? zp.y : zp.x);
        const uint32_t zz = PK2U(zf, zf);
        *(uint4*)(smem + OFF_KVB + hw * 2560 + 2048 + lane * 16) = make_uint4(zz, zz, zz, zz);
#pragma unroll
        for (int hh = 0; hh < 2; hh++) {
          const uint4* ff = &f[4 * hh];
          uint8_t* dst = smem + OFF_KVB + hw * 2560 + q * 512 + (16 * hh + g) * 16;
          *(uint4*)dst = make_uint4(PK2U(ff[0].x, ff[0].y), PK2U(ff[1].x, ff[1].y), PK2U(ff[2].x, ff[2].y), PK2U(ff[3].x, ff[3].y));
          *(uint4*)(dst + 128) = make_uint4(PK2U(ff[0].z, ff[0].w), PK2U(ff[1].z, ff[1].w), PK2U(ff[2].z, ff[2].w), PK2U(ff[3].z, ff[3].w));
        }
        fence_async();
        __syncwarp();
        if (lane == 0) { mbar_arrive(BAR(hw ? B_KV1 : B_KV)); if (hw == 0) STAMP(3, 9); }
      }
#define QBUF(ci) (sb + 2048 * (ci) + ((ci) < 6 ? OFF_STG : (ci) < 10 ? OFF_SPARE - 6 * 2048 : OFF_F2F - 10 * 2048))
      mbar_wait(BAR(B_Y), 0);
      if (elect_one()) {
        mbar_expect(sbar + 8, 4096);
#pragma unroll 1
        for (int ci = hw ? hw + 9 : 12; ci < 16; ci += 3) tma3d(QBUF(ci), &P.tmQ, 16 * cl, 64 * rank + 32, 2 * (ci & 7), sbar + 8);
      }
      mbar_wait(BAR(B_Q), 0);
      mbar_wait(sbar, hw == 0);
      {
        const float2 sc0 = *(const float2*)(smem + OFF_SCALE + 8 * q), sc1 = *(const float2*)(smem + OFF_SCALE + 32 + 8 * q);
        const uint32_t yl = sb + OFF_XT + (lane & 7) * XT_STRIDE + (lane >> 3) * 16;
#pragma unroll 1
        for (int ci = hw; ci < 16; ci += 3) {
          const uint32_t qb = QBUF(ci);
          if (ci >= 10) mbar_wait(sbar + 8, 1);
#pragma unroll 1
          for (int nl = 0; nl < 2; nl++) {
            uint32_t yy[2][4], qq[2][4];
            const uint32_t qa = qb + lane * 32 + ((lane & 4) << 2) + nl * 1024;
#pragma unroll
            for (int cg = 0; cg < 2; cg++) { ldsm4t(yy[cg], yl + cg * 2048 + (2 * ci + nl) * 64); ldsm4(qq[cg], qa ^ (cg * 16)); }
#pragma unroll
            for (int cg = 0; cg < 2; cg++) {
              const float2 sc = cg ? sc1 : sc0;
#pragma unroll
              for (int m = 0; m < 4; m++) {
                const float2 f = __half22float2(*(const __half2*)&yy[cg][m]);
                qq[cg][m] = hmul(qq[cg][m], pk2(f.x * sc.x, f.y * sc.y));
              }
              stsm4(qa ^ (cg * 16), qq[cg][0], qq[cg][1], qq[cg][2], qq[cg][3]);
            }
          }
          fence_async();
          __syncwarp();
          if (elect_one()) tma3d_st(&P.tmOA, qb, 16 * cl, 64 * rank + 32 * (ci >> 3), 2 * (ci & 7));
        }
        asm volatile("cp.async.bulk.commit_group;\ncp.async.bulk.wait_group.read 0;" ::: "memory");
      }
      if (lane == 0) STAMP(3, 10 + hw);
    }
    }
  }
}

typedef CUresult (*EncodeFn)(CUtensorMap*, CUtensorMapDataType, cuuint32_t, void*, const cuuint64_t*, const cuuint64_t*,
                             const cuuint32_t*, const cuuint32_t*, CUtensorMapInterleave, CUtensorMapSwizzle,
                             CUtensorMapL2promotion, CUtensorMapFloatOOBfill);

static void enc(EncodeFn fn, CUtensorMap* m, const void* p, int rank, const cuuint64_t* dims, const cuuint64_t* strides,
                const cuuint32_t* box, CUtensorMapSwizzle swz, CUtensorMapL2promotion promo) {
  cuuint32_t es[4] = {1, 1, 1, 1};
  fn(m, CU_TENSOR_MAP_DATA_TYPE_BFLOAT16, rank, (void*)p, dims, strides, box, es, CU_TENSOR_MAP_INTERLEAVE_NONE, swz, promo,
     CU_TENSOR_MAP_FLOAT_OOB_FILL_NONE);
}

extern "C" void kernel_launch(void* const* d_in, const int* in_sizes, int n_in, void* d_out, int out_size) {
  void* fp = nullptr;
  cudaDriverEntryPointQueryResult qr;
  cudaGetDriverEntryPoint("cuTensorMapEncodeTiled", &fp, cudaEnableDefault, &qr);
  EncodeFn fn = (EncodeFn)fp;
  Params P;
  P.shift_k = (const __nv_bfloat16*)d_in[3]; P.h = (const __nv_bfloat16*)d_in[4]; P.D = (const __nv_bfloat16*)d_in[5];
  P.q = (const __nv_bfloat16*)d_in[0];
  cudaGetSymbolAddress((void**)&P.part, g_part); cudaGetSymbolAddress((void**)&P.kv, g_kv); cudaGetSymbolAddress((void**)&P.o, g_o);
  cudaGetSymbolAddress((void**)&P.thr, c_thr); cudaGetSymbolAddress((void**)&P.img, c_img);
  P.x = (const __nv_bfloat16*)d_in[6]; P.w = (const __nv_bfloat16*)d_in[7]; P.wo = (const __nv_bfloat16*)d_in[8];
  const CUtensorMapSwizzle S128 = CU_TENSOR_MAP_SWIZZLE_128B, S32 = CU_TENSOR_MAP_SWIZZLE_32B;
  const CUtensorMapL2promotion P0 = CU_TENSOR_MAP_L2_PROMOTION_NONE, P128 = CU_TENSOR_MAP_L2_PROMOTION_L2_128B;
  { cuuint64_t d[2] = {1024, 2048}, s[1] = {2048}; cuuint32_t b[2] = {64, 128}; enc(fn, &P.tmX, d_in[6], 2, d, s, b, S128, P128); }
  { cuuint64_t d[2] = {1024, 2048}, s[1] = {2048}; cuuint32_t b[2] = {64, 64}; enc(fn, &P.tmX0, d_in[6], 2, d, s, b, S128, P128); }
  { cuuint64_t d[3] = {1024, 1024, 3}, s[2] = {6144, 2048}; cuuint32_t b[3] = {64, 64, 3}; enc(fn, &P.tmW, d_in[7], 3, d, s, b, S128, P128); }
  { cuuint64_t d[4] = {64, 64, 16, 16}, s[3] = {2048, 131072, 128}; cuuint32_t b[4] = {64, 32, 2, 2}; enc(fn, &P.tmWo, d_in[8], 4, d, s, b, S128, P128); }
  { cuuint64_t d[4] = {64, 64, 16, 16}, s[3] = {2048, 131072, 128}; cuuint32_t b[4] = {64, 32, 2, 1}; enc(fn, &P.tmWo1, d_in[8], 4, d, s, b, S128, P128); }
  { cuuint64_t d[2] = {1024, 2048}, s[1] = {2048}; cuuint32_t b[2] = {16, 72}; enc(fn, &P.tmK, d_in[1], 2, d, s, b, S32, P128); }
  { cuuint64_t d[2] = {1024, 2048}, s[1] = {2048}; cuuint32_t b[2] = {16, 64}; enc(fn, &P.tmV, d_in[2], 2, d, s, b, S32, P128); }
  { cuuint64_t d[3] = {1024, 128, 16}, s[2] = {32768, 2048}; cuuint32_t b[3] = {16, 32, 2}; enc(fn, &P.tmQ, d_in[0], 3, d, s, b, S32, P128); }
  { cuuint64_t d[3] = {1024, 128, 16}, s[2] = {65536, 4096}; cuuint32_t b[3] = {16, 32, 2}; enc(fn, &P.tmOA, d_out, 3, d, s, b, S32, P0); }
  { cuuint64_t d[2] = {2048, 2048}, s[1] = {4096}; cuuint32_t b[2] = {64, 16}; enc(fn, &P.tmOB, d_out, 2, d, s, b, S128, P0); }
  cudaFuncSetAttribute(fused_kernel, cudaFuncAttributeMaxDynamicSharedMemorySize, SMEM_TOTAL);
  fused_kernel<<<128, 384, SMEM_TOTAL>>>(P);
}
```

```cpp
#include <cuda_runtime.h>
#include <cuda_bf16.h>
#include <cuda_fp16.h>
#include <cuda.h>
#include <stdint.h>

template<int TA, int TB, int SA=1> __device__ __forceinline__ void wgmma_ss_n192(float (&d)[96], uint64_t da, uint64_t db, int scale_d) {
  asm volatile("{\n.reg .pred p;\nsetp.ne.b32 p, %98, 0;\n"
    "wgmma.mma_async.sync.aligned.m64n192k16.f32.bf16.bf16 {%0, %1, %2, %3, %4, %5, %6, %7, %8, %9, %10, %11, %12, %13, %14, %15, %16, %17, %18, %19, %20, %21, %22, %23, %24, %25, %26, %27, %28, %29, %30, %31, %32, %33, %34, %35, %36, %37, %38, %39, %40, %41, %42, %43, %44, %45, %46, %47, %48, %49, %50, %51, %52, %53, %54, %55, %56, %57, %58, %59, %60, %61, %62, %63, %64, %65, %66, %67, %68, %69, %70, %71, %72, %73, %74, %75, %76, %77, %78, %79, %80, %81, %82, %83, %84, %85, %86, %87, %88, %89, %90, %91, %92, %93, %94, %95}, %96, %97, p, %101, 1, %99, %100;\n}\n"
    : "+f"(d[0]), "+f"(d[1]), "+f"(d[2]), "+f"(d[3]), "+f"(d[4]), "+f"(d[5]), "+f"(d[6]), "+f"(d[7]), "+f"(d[8]), "+f"(d[9]), "+f"(d[10]), "+f"(d[11]), "+f"(d[12]), "+f"(d[13]), "+f"(d[14]), "+f"(d[15]), "+f"(d[16]), "+f"(d[17]), "+f"(d[18]), "+f"(d[19]), "+f"(d[20]), "+f"(d[21]), "+f"(d[22]), "+f"(d[23]), "+f"(d[24]), "+f"(d[25]), "+f"(d[26]), "+f"(d[27]), "+f"(d[28]), "+f"(d[29]), "+f"(d[30]), "+f"(d[31]), "+f"(d[32]), "+f"(d[33]), "+f"(d[34]), "+f"(d[35]), "+f"(d[36]), "+f"(d[37]), "+f"(d[38]), "+f"(d[39]), "+f"(d[40]), "+f"(d[41]), "+f"(d[42]), "+f"(d[43]), "+f"(d[44]), "+f"(d[45]), "+f"(d[46]), "+f"(d[47]), "+f"(d[48]), "+f"(d[49]), "+f"(d[50]), "+f"(d[51]), "+f"(d[52]), "+f"(d[53]), "+f"(d[54]), "+f"(d[55]), "+f"(d[56]), "+f"(d[57]), "+f"(d[58]), "+f"(d[59]), "+f"(d[60]), "+f"(d[61]), "+f"(d[62]), "+f"(d[63]), "+f"(d[64]), "+f"(d[65]), "+f"(d[66]), "+f"(d[67]), "+f"(d[68]), "+f"(d[69]), "+f"(d[70]), "+f"(d[71]), "+f"(d[72]), "+f"(d[73]), "+f"(d[74]), "+f"(d[75]), "+f"(d[76]), "+f"(d[77]), "+f"(d[78]), "+f"(d[79]), "+f"(d[80]), "+f"(d[81]), "+f"(d[82]), "+f"(d[83]), "+f"(d[84]), "+f"(d[85]), "+f"(d[86]), "+f"(d[87]), "+f"(d[88]), "+f"(d[89]), "+f"(d[90]), "+f"(d[91]), "+f"(d[92]), "+f"(d[93]), "+f"(d[94]), "+f"(d[95])
    : "l"(da), "l"(db), "r"(scale_d), "n"(TA), "n"(TB), "n"(SA));
}
template<int TA, int TB, int SA=1> __device__ __forceinline__ void wgmma_ss_n128(float (&d)[64], uint64_t da, uint64_t db, int scale_d) {
  asm volatile("{\n.reg .pred p;\nsetp.ne.b32 p, %66, 0;\n"
    "wgmma.mma_async.sync.aligned.m64n128k16.f32.bf16.bf16 {%0, %1, %2, %3, %4, %5, %6, %7, %8, %9, %10, %11, %12, %13, %14, %15, %16, %17, %18, %19, %20, %21, %22, %23, %24, %25, %26, %27, %28, %29, %30, %31, %32, %33, %34, %35, %36, %37, %38, %39, %40, %41, %42, %43, %44, %45, %46, %47, %48, %49, %50, %51, %52, %53, %54, %55, %56, %57, %58, %59, %60, %61, %62, %63}, %64, %65, p, %69, 1, %67, %68;\n}\n"
    : "+f"(d[0]), "+f"(d[1]), "+f"(d[2]), "+f"(d[3]), "+f"(d[4]), "+f"(d[5]), "+f"(d[6]), "+f"(d[7]), "+f"(d[8]), "+f"(d[9]), "+f"(d[10]), "+f"(d[11]), "+f"(d[12]), "+f"(d[13]), "+f"(d[14]), "+f"(d[15]), "+f"(d[16]), "+f"(d[17]), "+f"(d[18]), "+f"(d[19]), "+f"(d[20]), "+f"(d[21]), "+f"(d[22]), "+f"(d[23]), "+f"(d[24]), "+f"(d[25]), "+f"(d[26]), "+f"(d[27]), "+f"(d[28]), "+f"(d[29]), "+f"(d[30]), "+f"(d[31]), "+f"(d[32]), "+f"(d[33]), "+f"(d[34]), "+f"(d[35]), "+f"(d[36]), "+f"(d[37]), "+f"(d[38]), "+f"(d[39]), "+f"(d[40]), "+f"(d[41]), "+f"(d[42]), "+f"(d[43]), "+f"(d[44]), "+f"(d[45]), "+f"(d[46]), "+f"(d[47]), "+f"(d[48]), "+f"(d[49]), "+f"(d[50]), "+f"(d[51]), "+f"(d[52]), "+f"(d[53]), "+f"(d[54]), "+f"(d[55]), "+f"(d[56]), "+f"(d[57]), "+f"(d[58]), "+f"(d[59]), "+f"(d[60]), "+f"(d[61]), "+f"(d[62]), "+f"(d[63])
    : "l"(da), "l"(db), "r"(scale_d), "n"(TA), "n"(TB), "n"(SA));
}
template<int TA, int TB, int SA=1> __device__ __forceinline__ void wgmma_ss_n72(float (&d)[36], uint64_t da, uint64_t db, int scale_d) {
  asm volatile("{\n.reg .pred p;\nsetp.ne.b32 p, %38, 0;\n"
    "wgmma.mma_async.sync.aligned.m64n72k16.f32.bf16.bf16 {%0, %1, %2, %3, %4, %5, %6, %7, %8, %9, %10, %11, %12, %13, %14, %15, %16, %17, %18, %19, %20, %21, %22, %23, %24, %25, %26, %27, %28, %29, %30, %31, %32, %33, %34, %35}, %36, %37, p, %41, 1, %39, %40;\n}\n"
    : "+f"(d[0]), "+f"(d[1]), "+f"(d[2]), "+f"(d[3]), "+f"(d[4]), "+f"(d[5]), "+f"(d[6]), "+f"(d[7]), "+f"(d[8]), "+f"(d[9]), "+f"(d[10]), "+f"(d[11]), "+f"(d[12]), "+f"(d[13]), "+f"(d[14]), "+f"(d[15]), "+f"(d[16]), "+f"(d[17]), "+f"(d[18]), "+f"(d[19]), "+f"(d[20]), "+f"(d[21]), "+f"(d[22]), "+f"(d[23]), "+f"(d[24]), "+f"(d[25]), "+f"(d[26]), "+f"(d[27]), "+f"(d[28]), "+f"(d[29]), "+f"(d[30]), "+f"(d[31]), "+f"(d[32]), "+f"(d[33]), "+f"(d[34]), "+f"(d[35])
    : "l"(da), "l"(db), "r"(scale_d), "n"(TA), "n"(TB), "n"(SA));
}
template<int TB, int SA=1> __device__ __forceinline__ void wgmma_rs_n40(float (&d)[20], uint32_t a0, uint32_t a1, uint32_t a2, uint32_t a3, uint64_t db, int scale_d) {
  asm volatile("{\n.reg .pred p;\nsetp.ne.b32 p, %25, 0;\n"
    "wgmma.mma_async.sync.aligned.m64n40k16.f32.bf16.bf16 {%0, %1, %2, %3, %4, %5, %6, %7, %8, %9, %10, %11, %12, %13, %14, %15, %16, %17, %18, %19}, {%20, %21, %22, %23}, %24, p, %27, 1, %26;\n}\n"
    : "+f"(d[0]), "+f"(d[1]), "+f"(d[2]), "+f"(d[3]), "+f"(d[4]), "+f"(d[5]), "+f"(d[6]), "+f"(d[7]), "+f"(d[8]), "+f"(d[9]), "+f"(d[10]), "+f"(d[11]), "+f"(d[12]), "+f"(d[13]), "+f"(d[14]), "+f"(d[15]), "+f"(d[16]), "+f"(d[17]), "+f"(d[18]), "+f"(d[19])
    : "r"(a0), "r"(a1), "r"(a2), "r"(a3), "l"(db), "r"(scale_d), "n"(TB), "n"(SA));
}
template<int TB> __device__ __forceinline__ void wgmma_hrs_n64(uint32_t (&d)[16], uint32_t a0, uint32_t a1, uint32_t a2, uint32_t a3, uint64_t db, int scale_d) {
  asm volatile("{\n.reg .pred p;\nsetp.ne.b32 p, %21, 0;\n"
    "wgmma.mma_async.sync.aligned.m64n64k16.f16.f16.f16 {%0, %1, %2, %3, %4, %5, %6, %7, %8, %9, %10, %11, %12, %13, %14, %15}, {%16, %17, %18, %19}, %20, p, 1, 1, %22;\n}\n"
    : "+r"(d[0]), "+r"(d[1]), "+r"(d[2]), "+r"(d[3]), "+r"(d[4]), "+r"(d[5]), "+r"(d[6]), "+r"(d[7]), "+r"(d[8]), "+r"(d[9]), "+r"(d[10]), "+r"(d[11]), "+r"(d[12]), "+r"(d[13]), "+r"(d[14]), "+r"(d[15])
    : "r"(a0), "r"(a1), "r"(a2), "r"(a3), "l"(db), "r"(scale_d), "n"(TB));
}
template<int TB> __device__ __forceinline__ void wgmma_hrs_n32(uint32_t (&d)[8], uint32_t a0, uint32_t a1, uint32_t a2, uint32_t a3, uint64_t db, int scale_d) {
  asm volatile("{\n.reg .pred p;\nsetp.ne.b32 p, %13, 0;\n"
    "wgmma.mma_async.sync.aligned.m64n32k16.f16.f16.f16 {%0, %1, %2, %3, %4, %5, %6, %7}, {%8, %9, %10, %11}, %12, p, 1, 1, %14;\n}\n"
    : "+r"(d[0]), "+r"(d[1]), "+r"(d[2]), "+r"(d[3]), "+r"(d[4]), "+r"(d[5]), "+r"(d[6]), "+r"(d[7])
    : "r"(a0), "r"(a1), "r"(a2), "r"(a3), "l"(db), "r"(scale_d), "n"(TB));
}

__device__ __align__(128) const uint32_t c_thr[1536] = {
  0x33fb33ff,0xa49c9de4,0x33273352,0xaf2cae76,0x33e233f1,0xa96ca7bd,0x32c432f7,0xb045afdd,0x33b733cf,0xac3eaaf7,0x3250328c,0xb0eab099,
  0x3378339a,0xadbcacff,0x31cd3211,0xb182b137,0x33d033fb,0xaadea46a,0x299e2d17,0xb3e0b396,0x32fb337a,0xafd2adb1,0xa78b1f76,0xb3f2b3ff,
  0x318b3254,0xb1c5b0e5,0xae6bac32,0xb354b3b8,0x2f4230a3,0xb321b285,0xb133b040,0xb215b2c7,0x337c33f2,0xada5a759,0xb179afc8,0xb1d6b2fe,
  0x31463293,0xb204b08e,0xb394b2ba,0xad23b055,0x2b402f4e,0xb3cbb31e,0xb3e4b3f9,0x293ba533,0xac269c52,0xb3bab400,0xb258b357,0x30e02e5f,
  0x330133e5,0xafbda922,0xb3f3b3c9,0x2727ab59,0x2deb314a,0xb36fb200,0xb194b32f,0x31bc2f0a,0xacdb2084,0xb39fb3ff,0xa565aea4,0x33f93347,
  0xb2b6b0db,0xb05ab25c,0x30892c1a,0x329733bc,0x326033d4,0xb0d6aa94,0xb00ab29b,0x32e83084,0x20e82f64,0xb3feb318,0x2d8da597,0x338133f8,
  0xb1fcae48,0xb14fb35c,0x339031b8,0x2d3a3199,0xb3e6b3ae,0x2909ac7b,0x32d133f4,0xb030a6f5,0x319d33bf,0xb1b3ac02,0x2e3ca874,0x335e33ec,
  0xacc32b89,0xb3a3b3c6,0x33f83276,0x25c930b7,0xb3dcb1f8,0xaa01b154,0x30653335,0xb2b0aef4,0xb107b383,0x32392d81,0xafa6214d,0xb307b3fe,
  0x30bc33a5,0xb273acb7,0x33c5311b,0x2ba23229,0xb0cc94b6,0xb267b400,0x30153360,0xb2e1ae31,0xb385b3ab,0x2d76ac93,0xb166a691,0xb1e7b3f5,
  0x22deb06a,0x33fd32ac,0xb337b3da,0x2ee8aa19,0x2f853387,0xb310ad6a,0x322d33fe,0xb1162216,0xb2a9abd3,0xb06fb3c2,0xb07428a6,0xb2a5b3ea,
  0xb111b3e9,0x323128be,0xb30db3c3,0x2f90abba,0x31aa227a,0x31a633fd,0x2e25ad5e,0x33633389,0x2d6a3365,0xb387ae1a,0xa21631aa,0xb3feb1a6,
  0xb3c2af85,0xabd3b310,0xb3eab22d,0x28a6b116,0xa8beb2a9,0x33e9306f,0x2bbab074,0x33c332a5,0x33fd3111,0x227a3231,0x3389330d,0xad5e2f90,
  0x2a63333f,0xb3d7aec6,0xb2a2a1b1,0xb07ab3fe,0xb3f7b158,0x25fbb1f4,0xacb7b38b,0x33a52d52,0x2e0eb025,0x336832d8,0x340030bc,0x14b63273,
  0x323533c0,0xb10c2beb,0xac9330cc,0xb3abb267,0x23433316,0xb3fdaf6f,0xb38eb225,0x2d46b11f,0xb342b29e,0x2ebbb07f,0x31e3aa7c,0x316b33d6,
  0x3264a6c3,0x30d133f5,0x2c0233ac,0xb3bfac87,0x28f0336a,0xb3e7ae02,0xb3c6b19d,0x2b89b1b3,0xa59732e8,0xb3f8b00a,0xaccfb3ed,0x33a1285b,
  0xb1b8b381,0x3199ad8d,0x336c31df,0xadf73170,0x33f42d3a,0x26f53390,0xb30423a7,0xafb2b3fc,0xb05f3030,0xb2b3b2d1,0x29e8b27a,0x33dd30b2,
  0xab5932b6,0xb3c9b05a,0x30adb089,0x327e3297,0xaf0ab3f3,0x332fa727,0x240633b0,0xb3fcac6f,0x33473194,0xaea431bc,0xb174b359,0x31daae54,
  0xb3bca565,0xac1ab3f9,0x33ee2f59,0xa842331b,0xaddf3281,0xb371b0a8,0x34002b40,0x1c5233cb,0xa759b3ef,0x33f22829,0xb2fe2c26,0xafc8b3ba,
  0x308e337c,0xb2932da5,0x3055b179,0x32ba31d6,0xb31eb146,0x2f4eb204,0xa5333394,0xb3f9ad23,0xaff33249,0xb2f1b0f3,0x30e532fb,0xb2542fd2,
  0x2b28b373,0x33cc2dd4,0xb285b18b,0x30a3b1c5,0x246a33fa,0xb3fba500,0x33962f42,0xad173321,0xadb1b3d0,0x337aaade,0xb3ffa99e,0x1f76b3e0,
  0xb0ee320d,0xb24db13c,0xac4b3398,0xb3b5ad0b,0x304ab289,0x32c1309e,0x2985b3ce,0x33e12b0f,0xaf3732f4,0xb324afe8,0xa4ce33f0,0xb3faa7ef,
  0x2dc8b34f,0x33762e82,0x9de4b3ff,0x33ff1ead,0xb1c931cd,0xb186b182,0xb3762e82,0xadc8b34f,0x324db13c,0x30ee320d,0x33b5ad0b,0x2c4b3398,
  0xb2c1309e,0xb04ab289,0xb3e12b0f,0xa985b3ce,0x3324afe8,0x2f3732f4,0x33faa7ef,0x24ce33f0,0xb285318b,0xb0a3b1c5,0xb2c7ae6b,0x3040b354,
  0x3396af42,0x2d173321,0x31413133,0xb2093215,0xb3ff299e,0x9f76b3e0,0xae8db2bd,0x334cb050,0x33b8278b,0xac3233f2,0x281033b3,0xb3ef2c57,
  0xb31e3146,0xaf4eb204,0xa533b394,0x33f9ad23,0x3400ab40,0x9c5233cb,0xae5f33e4,0xb357a93b,0xb2feac26,0x2fc8b3ba,0x3245b258,0x30f830e0,
  0x30553179,0xb2ba31d6,0xb3df2e99,0xa9b6b34a,0xb39230fd,0xad2fb241,0x3200b301,0x314a2fbd,0x337f1b11,0xad993400,0xb3ff2deb,0xa084b36f,
  0xb005b129,0x32ebb21d,0x325c2cdb,0xb0db339f,0xa92233de,0xb3e529cf,0xab59b2b6,0x33c9b05a,0xb3dd30b2,0xa9e8b27a,0x33d4ab71,0xaa9433c8,
  0x32212c0e,0xb12433bd,0xaf64b0d6,0x3318b260,0x197fb345,0x3400aeaf,0xae4833fe,0xb35c20e8,0xb23d3332,0xb102aeff,0x33aeb14f,0x2c7b31fc,
  0xb3fe3065,0xa14db2b0,0x2ebb307f,0xb342329e,0x300f2fa6,0xb2e53307,0x30d1b3f5,0x326426c3,0x302ab400,0x32d517db,0xb3e72e02,0x28f0b36a,
  0xb3fd2f6f,0x2343b316,0x2d46311f,0xb38e3225,0xb3f53015,0x2691b2e1,0xaf9b33eb,0xb30a288d,0x2a193166,0xb3da31e7,0x33d7aec6,0xaa63333f,
  0x3313b337,0x2f7a2ee8,0xa5fbb1f4,0x33f7b158,0xb1a1a8d7,0x31afb3e8,0xb36832d8,0xae0eb025,0xb3c22f85,0x2bd3b310,0xb3ea322d,0xa8a6b116,
  0xa8be32a9,0xb3e9306f,0x2bba3074,0xb3c332a5,0x33fdb111,0xa27a3231,0x3389b30d,0x2d5e2f90,0xa216b1aa,0x33feb1a6,0xaed2ae25,0x333db363,
  0xb3652edd,0x2e1ab33a,0xb1aa227a,0x31a6b3fd,0xaf853387,0xb3102d6a,0xb22d33fe,0xb116a216,0x32a9abd3,0xb06f33c2,0x307428a6,0xb2a533ea,
  0x3111b3e9,0x3231a8be,0x330db3c3,0x2f902bba,0xb2e12e31,0x3015b360,0x288db1a1,0x33ebb1af,0xb1e733f5,0xb1662691,0xb33f2f9b,0x2ec6b30a,
  0x2ee82a19,0xb33733da,0xb15833d7,0xb1f42a63,0x33e8b313,0x28d72f7a,0x302525fb,0xb2d833f7,0xb2392d81,0x3107b383,0x3307b3fe,0x2fa6214d,
  0xb35e33ec,0xae3ca874,0x97dbb00f,0x3400b2e5,0xa5c930b7,0xb3f83276,0xb316302a,0x2f6fb2d5,0x32b0aef4,0xb0653335,0xb29e33fd,0xb07f2343,
  0xb1702ccf,0x31dfb3a1,0x3345b124,0xaeaf3221,0xb3fc336c,0xa3a7adf7,0x3332b400,0x2eff997f,0xb0b23304,0xb27a2fb2,0x2b71b102,0x33c8b23d,
  0x2c0e29e8,0xb3bd33dd,0xb0d62a94,0x3260b3d4,0xb0892c1a,0x3297b3bc,0x2aad2842,0xb3d333ee,0xb3b0327e,0x2c6fb0ad,0x3241b035,0xb0fd32ce,
  0xb35933fc,0xae542406,0x3400b392,0x1b112d2f,0xaf5931da,0xb31b3174,0x321db37f,0x3129ad99,0xaf152ac6,0x332cb3d2,0xb1463293,0xb204308e,
  0xb281312e,0x30a8b219,0xab402f4e,0xb3cb331e,0xb3ef3371,0x2829addf,0x2c269c52,0xb3ba3400,0xb37c33f2,0xada52759,0x3179afc8,0xb1d632fe,
  0xacf32953,0x339cb3e3,0xb3fa33cc,0x2500ab28,0xb0942f21,0x3290b32a,0xb3d033fb,0xaade246a,0xb249317d,0x30f3b1d2,0xb2fb337a,0xafd22db1,
  0xb37332f1,0x2dd4aff3,0xb18b3254,0xb1c530e5,0xa96c27bd,0x33e2b3f1,0xb0452fdd,0x32c4b2f7,0xac3e2af7,0x33b7b3cf,0xb0ea3099,0x3250b28c,
  0xadbc2cff,0x3378b39a,0xb1823137,0x31cdb211,0xaf2c2e76,0x3327b352,0xb20d31c9,0x313cb186,0x313c3186,0xb20db1c9,0x2d0b2dc8,0xb398b376,
  0x309e30ee,0xb289b24d,0x2b0f2c4b,0xb3ceb3b5,0x2fe8304a,0xb2f4b2c1,0x27ef2985,0xb3f0b3e1,0x2e822f37,0xb34fb324,0x1ead24ce,0xb3ffb3fa,
  0xb2bdb209,0xb050b141,0xb290b32a,0x30942f21,0xb3b3b34c,0xac57ae8d,0xb0f3b1d2,0x3249317d,0xb400b3ef,0x1d1ba810,0xadd4aff3,0x337332f1,
  0xb39cb3e3,0x2cf32953,0xa500ab28,0x33fa33cc,0xae99b0f8,0x334a3245,0x33ff33b2,0x201f2c63,0x2438a9b6,0x33fc33df,0x332c33d2,0xaf15aac6,
  0x303a2ce7,0x32cb339e,0x30a83219,0xb281b12e,0x32ee31c0,0x2ffe3190,0x28292ddf,0xb3efb371,0x33b0327e,0x2c6f30ad,0xb241b035,0xb0fdb2ce,
  0x335933fc,0xae54a406,0xb400b392,0x1b11ad2f,0x2f5931da,0xb31bb174,0xb21db37f,0x31292d99,0xaaad2842,0xb3d3b3ee,0xa9cfb005,0x33de32eb,
  0x285b305f,0xb3edb2b3,0x2c0ea9e8,0x33bd33dd,0xb170accf,0xb1dfb3a1,0x33453124,0x2eaf3221,0xb3fcb36c,0x23a7adf7,0x33323400,0xaeff997f,
  0xb0b2b304,0x327a2fb2,0x2b713102,0xb3c8b23d,0xb400b2e5,0x17dbb00f,0x2e023264,0xb36ab0d1,0xaf6fb2d5,0x3316302a,0xb11fa8f0,0xb225b3e7,
  0x307f2343,0x329e33fd,0xb3d6b38e,0x2a7cad46,0x33f53342,0xa6c32ebb,0xac87b1e3,0x33ac316b,0x28d7af7a,0x33e83313,0xb2d8b3f7,0x3025a5fb,
  0x33eb31af,0x288d31a1,0x2bebae0e,0x33c03368,0x2ec6330a,0xb33faf9b,0x33fe3235,0x21b1310c,0xb1f4aa63,0xb158b3d7,0x2d5232a2,0xb38bb07a,
  0x33a7333d,0xacab2ed2,0x33f63162,0x262d31eb,0xaa4b301a,0xb3d8b2de,0x2a32326b,0xb3d9b0c7,0xb3f6b26f,0x265fb0c1,0xb3a9b020,0xac9fb2db,
  0x0e48b15d,0x340031f0,0xae1ab33a,0x33652edd,0xaed22e25,0xb33db363,0xb1eb0e48,0xb162b400,0xb2deb3a7,0x301aacab,0xb0c7b3f6,0x326b262d,
  0x30c1aa4b,0x326f33d8,0x32db2a32,0x302033d9,0x31f033f6,0xb15d265f,0x2edd33a9,0xb33aac9f,0xb2acb385,0x306aad76,0x2a19b166,0x33da31e7,
  0x3229a2de,0x311b33fd,0x33133337,0xaf7a2ee8,0x2e3133c5,0xb360aba2,0xb1a128d7,0xb1afb3e8,0xb3f5b015,0xa691b2e1,0xaf9bb3eb,0x330a288d,
  0x3154acc3,0x31f833a3,0x2ef433f8,0xb335a5c9,0x2d8133dc,0xb383aa01,0xb3feb065,0x214db2b0,0xb3ecb107,0x2874b239,0x300fafa6,0x32e53307,
  0x30b7ae3c,0x3276335e,0x302a3400,0xb2d517db,0x312433bd,0xb2212c0e,0xb318b260,0x2f64b0d6,0xb400aeaf,0x997fb345,0x335c20e8,0x2e4833fe,
  0x3102aeff,0x323d3332,0xac7b31fc,0xb3aeb14f,0x2a9433c8,0xb3d4ab71,0xb084b3e6,0x329ba909,0xb2ce2aad,0xb035b3d3,0x33e529cf,0x292233de,
  0x2d2fb241,0x339230fd,0xb14a2fbd,0xb200b301,0x2d993400,0xb37f1b11,0x2084b36f,0x33ff2deb,0xb2ebb21d,0x3005b129,0x30db339f,0xb25c2cdb,
  0xae5fb3e4,0x3357a93b,0xb190303a,0xb1c0b2cb,0x32453258,0xb0f830e0,0x2c63b2ee,0x33b22ffe,0xb3dfae99,0x29b6b34a,0x2ac633ff,0xb3d2a01f,
  0x339ea438,0x2ce733fc,0xb12eb32c,0x3219af15,0x33b8a78b,0x2c3233f2,0x2810b3b3,0x33ef2c57,0xb2c72e6b,0xb040b354,0x29533400,0xb3e31d1b,
  0x3141b133,0x32093215,0xaf21b39c,0x332aacf3,0xae8d32bd,0xb34cb050,0x317d3290,0xb1d23094,0x27bd33fb,0xb3f1249c,0x2fdd3327,0xb2f72f2c,
  0xaaf7b3e2,0x33cfa96c,0xb099b2c4,0x328cb045,0x2cff33b7,0xb39a2c3e,0x31373250,0xb21130ea,0xae76b378,0x3352adbc,0xb1c9b1cd,0x3186b182,
  0xb3ff1ead,0x1de4b3ff,0xb352adbc,0x2e76b378,0x33f1249c,0xa7bd33fb,0x32f72f2c,0xafdd3327,0xb3cfa96c,0x2af7b3e2,0xb28cb045,0x3099b2c4,
  0x339a2c3e,0xacff33b7,0x321130ea,0xb1373250,0x2953b400,0x33e31d1b,0x33ccadd4,0x2b283373,0xaf21339c,0xb32aacf3,0xb3fb2500,0x246ab3fa,
  0x317db290,0x31d23094,0x337a2ade,0xadb133d0,0xb2f130f3,0xaff3b249,0xb254afd2,0x30e5b2fb,0x339e2438,0xace733fc,0xb12e332c,0xb219af15,
  0xb190b03a,0x31c0b2cb,0x3371b0a8,0x2ddf3281,0x2c6332ee,0xb3b22ffe,0xb3f22829,0x2759b3ef,0x2ac6b3ff,0x33d2a01f,0x32932da5,0xb08e337c,
  0xaf0a33f3,0xb32fa727,0x2406b3b0,0x33fcac6f,0x3347b194,0x2ea431bc,0xb1743359,0xb1daae54,0xb3bc2565,0x2c1ab3f9,0x33eeaf59,0x2842331b,
  0x30ad3089,0xb27e3297,0xb2ceaaad,0x3035b3d3,0xb29ba909,0x3084b3e6,0x305f3030,0xb2b332d1,0x259732e8,0xb3f8300a,0x2ccfb3ed,0x33a1a85b,
  0x31b8b381,0x31992d8d,0xb36c31df,0xadf7b170,0xb3f42d3a,0x26f5b390,0x330423a7,0xafb233fc,0x316bb3d6,0x31e32a7c,0xb3832a01,0x2d81b3dc,
  0xb3bf2c87,0x2c02b3ac,0x28743239,0xb3ec3107,0x2b8931b3,0xb3c6319d,0x3276b35e,0x30b72e3c,0x31f8b3a3,0x31542cc3,0xb33525c9,0x2ef4b3f8,
  0x310c2beb,0xb23533c0,0x33abb267,0x2c9330cc,0x307ab3fe,0x32a2a1b1,0xb06aad76,0x32acb385,0xb3a52d52,0x2cb7b38b,0xb11b33fd,0xb229a2de,
  0x94b63273,0xb40030bc,0x3360aba2,0xae3133c5,0xb2de33a7,0xb01aacab,0xb0c733f6,0xb26b262d,0x30c12a4b,0xb26f33d8,0x32dbaa32,0xb02033d9,
  0x31f0b3f6,0x315d265f,0x2eddb3a9,0x333aac9f,0xb1eb8e48,0x3162b400,0xb3872e1a,0x2d6ab365,0xae25ad5e,0x3363b389,0x8e48b15d,0x3400b1f0,
  0xb3a7333d,0xacabaed2,0xb3f63162,0x262db1eb,0x2a4b301a,0xb3d832de,0xaa32326b,0xb3d930c7,0x33f6b26f,0x265f30c1,0x33a9b020,0xac9f32db,
  0x33c0b368,0x2beb2e0e,0x30cc94b6,0xb2673400,0x21b1b10c,0x33feb235,0x3385b3ab,0x2d762c93,0xb38b307a,0x2d52b2a2,0xa2deb06a,0x33fdb2ac,
  0xb0bc33a5,0xb2732cb7,0xb3c5311b,0x2ba2b229,0x26c32ebb,0xb3f53342,0xb3ac316b,0x2c87b1e3,0x336ab0d1,0xae023264,0xb19d33bf,0xb1b32c02,
  0x3225b3e7,0x311fa8f0,0x2cc32b89,0xb3a333c6,0xaa7cad46,0x33d6b38e,0x33dcb1f8,0xaa013154,0xb3fe3318,0x20e8af64,0x3381b3f8,0x2d8d2597,
  0xb14f335c,0xb1fc2e48,0x2d3ab199,0x3390b1b8,0x29092c7b,0xb3e633ae,0xb03026f5,0x32d1b3f4,0x32e8b084,0xb00a329b,0xb3ed32b3,0x285bb05f,
  0x29cfb005,0x33deb2eb,0xb05a325c,0xb2b630db,0xafbd2922,0x3301b3e5,0x27272b59,0xb3f333c9,0xb36f3200,0x2debb14a,0x31bcaf0a,0xb194332f,
  0xb39f33ff,0xacdba084,0x33f9b347,0xa5652ea4,0x3394b2ba,0xad233055,0xa438a9b6,0x33fcb3df,0x33e4b3f9,0x293b2533,0xb03a2ce7,0x32cbb39e,
  0x3258b357,0x30e0ae5f,0xb2ee31c0,0x2ffeb190,0x2e99b0f8,0x334ab245,0xb3ff33b2,0x201fac63,0xaf4230a3,0xb3213285,0x3133b040,0xb21532c7,
  0xa99e2d17,0xb3e03396,0x32bdb209,0xb0503141,0x278b1f76,0xb3f233ff,0x33b3b34c,0xac572e8d,0x2e6bac32,0xb35433b8,0x3400b3ef,0x1d1b2810,
  0xb289324d,0x309eb0ee,0xb3ce33b5,0x2b0fac4b,0xb2f432c1,0x2fe8b04a,0xb3f033e1,0x27efa985,0xb34f3324,0x2e82af37,0xb3ff33fa,0x1eada4ce,
  0xb3983376,0x2d0badc8,0xb3fb33ff,0xa49c1de4,0x351c35f6,0xac93a617,0xb8a3b93c,0x308d2a16,0x32f43448,0xb160afa5,0xb6a4b7fe,0x353a3389,
  0x2fa53160,0xb448b2f4,0xb389b53a,0x37fe36a4,0x26172c93,0xb5f6b51c,0xaa16b08d,0x393c38a3,0x34c3358c,0xac47a5b2,0xb85fb8f3,0x304229b1,
  0x327e33fd,0xb106af26,0xb63cb785,0x34e7330f,0x2f263106,0xb3fdb27e,0xb30fb4e7,0x3785363c,0x25b22c47,0xb58cb4c3,0xa9b1b042,0x38f3385f,
  0x346a3523,0xabf6a54d,0xb81ab8a8,0x2fef294d,0x3209336b,0xb0acaea7,0xb5d4b70a,0x34933294,0x2ea730ac,0xb36bb209,0xb294b493,0x370a35d4,
  0x254d2bf6,0xb523b46a,0xa94dafef,0x38a8381a,0x341334bc,0xab5fa4e9,0xb7a6b85a,0x2f5928e8,0x319432da,0xb052ae28,0xb56ab68d,0x343e3219,
  0x2e283052,0xb2dab194,0xb219b43e,0x368d356a,0x24e92b5f,0xb4bcb413,0xa8e8af59,0x385a37a6,0x33783456,0xaac8a484,0xb715b80a,0x2ec32884,
  0x3120324a,0xaff2ada9,0xb4ffb60e,0x33d3319e,0x2da92ff2,0xb24ab120,0xb19eb3d3,0x360e34ff,0x24842ac8,0xb456b378,0xa884aec3,0x380a3715,
  0x32cd33e3,0xaa31a420,0xb682b76f,0x2e2d281f,0x30ac31bb,0xaf3fad2a,0xb493b58d,0x33283122,0x2d2a2f3f,0xb1bbb0ac,0xb122b328,0x358d3493,
  0x24202a31,0xb3e3b2cd,0xa81fae2d,0x376f3682,0x3223331c,0xa999a376,0xb5ebb6c6,0x2d972776,0x3039312d,0xae8dacac,0xb426b50b,0x327c30a6,
  0x2cac2e8d,0xb12db039,0xb0a6b27c,0x350b3426,0x23762999,0xb31cb223,0xa776ad97,0x36c635eb,0x317a3257,0xa902a2ad,0xb552b61a,0x2d0026ad,
  0x2f8c309f,0xaddcac2e,0xb371b487,0x31cf3029,0x2c2e2ddc,0xb09faf8c,0xb029b1cf,0x34873371,0x22ad2902,0xb257b17a,0xa6adad00,0x361a3552,
  0x30d23194,0xa86ba1e4,0xb4b7b56a,0x2c6a25e4,0x2ea73012,0xad2aab5f,0xb294b402,0x31222f59,0x2b5f2d2a,0xb012aea7,0xaf59b122,0x34023294,
  0x21e4286b,0xb194b0d2,0xa5e4ac6a,0x356a34b7,0x302c30d2,0xa7a9a11b,0xb41ab4b7,0x2ba7251b,0x2dc22f0c,0xac79aa63,0xb1b6b2f7,0x30742e5f,
  0x2a632c79,0xaf0cadc2,0xae5fb074,0x32f731b6,0x211b27a9,0xb0d2b02c,0xa51baba7,0x34b7341a,0x2f0c3012,0xa67ba052,0xb2f7b402,0x2a7a2452,
  0x2cde2df5,0xab91a967,0xb0d7b1e8,0x2f8b2d65,0x29672b91,0xadf5acde,0xad65af8b,0x31e830d7,0x2052267b,0xb012af0c,0xa452aa7a,0x340232f7,
  0x2dc22ea7,0xa54d9f12,0xb1b6b294,0x294d2311,0x2bf62cde,0xaa31a86b,0xafefb0d7,0x2e2d2c6a,0x286b2a31,0xacdeabf6,0xac6aae2d,0x30d72fef,
  0x1f12254d,0xaea7adc2,0xa311a94d,0x329431b6,0x2c792d2a,0xa4209d7f,0xb074b122,0x281f217f,0x2a312b91,0xa8d0a6e0,0xae2daf8b,0x2cce2ade,
  0x26e028d0,0xab91aa31,0xaadeacce,0x2f8b2e2d,0x1d7f2420,0xad2aac79,0xa17fa81f,0x31223074,0x2a632b5f,0xa1e49bdb,0xae5faf59,0x25e41fdb,
  0x286b2967,0xa6e0a4e9,0xac6aad65,0x2ade28e8,0x24e926e0,0xa967a86b,0xa8e8aade,0x2d652c6a,0x1bdb21e4,0xab5faa63,0x9fdba5e4,0x2f592e5f,
  0x27a9286b,0x9f1298b6,0xaba7ac6a,0x23111cb6,0x254d267b,0xa420a1e4,0xa94daa7a,0x281f25e4,0x21e42420,0xa67ba54d,0xa5e4a81f,0x2a7a294d,
  0x18b61f12,0xa86ba7a9,0x9cb6a311,0x2c6a2ba7,0x211b21e4,0x98b69248,0xa51ba5e4,0x1cb61648,0x1f122052,0x9d7f9bdb,0xa311a452,0x217f1fdb,
  0x1bdb1d7f,0xa0529f12,0x9fdba17f,0x24522311,0x124818b6,0xa1e4a11b,0x96489cb6,0x25e4251b,0xa11ba1e4,0x18b61248,0x251b25e4,0x9cb69648,
  0x9f12a052,0x1d7f1bdb,0x23112452,0xa17f9fdb,0x9bdb9d7f,0x20521f12,0x1fdb217f,0xa452a311,0x924898b6,0x21e4211b,0x16481cb6,0xa5e4a51b,
  0xa7a9a86b,0x1f1218b6,0x2ba72c6a,0xa3119cb6,0xa54da67b,0x242021e4,0x294d2a7a,0xa81fa5e4,0xa1e4a420,0x267b254d,0x25e4281f,0xaa7aa94d,
  0x98b69f12,0x286b27a9,0x1cb62311,0xac6aaba7,0xaa63ab5f,0x21e41bdb,0x2e5f2f59,0xa5e49fdb,0xa86ba967,0x26e024e9,0x2c6a2d65,0xaadea8e8,
  0xa4e9a6e0,0x2967286b,0x28e82ade,0xad65ac6a,0x9bdba1e4,0x2b5f2a63,0x1fdb25e4,0xaf59ae5f,0xac79ad2a,0x24201d7f,0x30743122,0xa81fa17f,
  0xaa31ab91,0x28d026e0,0x2e2d2f8b,0xacceaade,0xa6e0a8d0,0x2b912a31,0x2ade2cce,0xaf8bae2d,0x9d7fa420,0x2d2a2c79,0x217f281f,0xb122b074,
  0xadc2aea7,0x254d1f12,0x31b63294,0xa94da311,0xabf6acde,0x2a31286b,0x2fef30d7,0xae2dac6a,0xa86baa31,0x2cde2bf6,0x2c6a2e2d,0xb0d7afef,
  0x9f12a54d,0x2ea72dc2,0x2311294d,0xb294b1b6,0xaf0cb012,0x267b2052,0x32f73402,0xaa7aa452,0xacdeadf5,0x2b912967,0x30d731e8,0xaf8bad65,
  0xa967ab91,0x2df52cde,0x2d652f8b,0xb1e8b0d7,0xa052a67b,0x30122f0c,0x24522a7a,0xb402b2f7,0xb02cb0d2,0x27a9211b,0x341a34b7,0xaba7a51b,
  0xadc2af0c,0x2c792a63,0x31b632f7,0xb074ae5f,0xaa63ac79,0x2f0c2dc2,0x2e5f3074,0xb2f7b1b6,0xa11ba7a9,0x30d2302c,0x251b2ba7,0xb4b7b41a,
  0xb0d2b194,0x286b21e4,0x34b7356a,0xac6aa5e4,0xaea7b012,0x2d2a2b5f,0x32943402,0xb122af59,0xab5fad2a,0x30122ea7,0x2f593122,0xb402b294,
  0xa1e4a86b,0x319430d2,0x25e42c6a,0xb56ab4b7,0xb17ab257,0x290222ad,0x3552361a,0xad00a6ad,0xaf8cb09f,0x2ddc2c2e,0x33713487,0xb1cfb029,
  0xac2eaddc,0x309f2f8c,0x302931cf,0xb487b371,0xa2ada902,0x3257317a,0x26ad2d00,0xb61ab552,0xb223b31c,0x29992376,0x35eb36c6,0xad97a776,
  0xb039b12d,0x2e8d2cac,0x3426350b,0xb27cb0a6,0xacacae8d,0x312d3039,0x30a6327c,0xb50bb426,0xa376a999,0x331c3223,0x27762d97,0xb6c6b5eb,
  0xb2cdb3e3,0x2a312420,0x3682376f,0xae2da81f,0xb0acb1bb,0x2f3f2d2a,0x3493358d,0xb328b122,0xad2aaf3f,0x31bb30ac,0x31223328,0xb58db493,
  0xa420aa31,0x33e332cd,0x281f2e2d,0xb76fb682,0xb378b456,0x2ac82484,0x3715380a,0xaec3a884,0xb120b24a,0x2ff22da9,0x34ff360e,0xb3d3b19e,
  0xada9aff2,0x324a3120,0x319e33d3,0xb60eb4ff,0xa484aac8,0x34563378,0x28842ec3,0xb80ab715,0xb413b4bc,0x2b5f24e9,0x37a6385a,0xaf59a8e8,
  0xb194b2da,0x30522e28,0x356a368d,0xb43eb219,0xae28b052,0x32da3194,0x3219343e,0xb68db56a,0xa4e9ab5f,0x34bc3413,0x28e82f59,0xb85ab7a6,
  0xb46ab523,0x2bf6254d,0x381a38a8,0xafefa94d,0xb209b36b,0x30ac2ea7,0x35d4370a,0xb493b294,0xaea7b0ac,0x336b3209,0x32943493,0xb70ab5d4,
  0xa54dabf6,0x3523346a,0x294d2fef,0xb8a8b81a,0xb4c3b58c,0x2c4725b2,0x385f38f3,0xb042a9b1,0xb27eb3fd,0x31062f26,0x363c3785,0xb4e7b30f,
  0xaf26b106,0x33fd327e,0x330f34e7,0xb785b63c,0xa5b2ac47,0x358c34c3,0x29b13042,0xb8f3b85f,0xb51cb5f6,0x2c932617,0x38a3393c,0xb08daa16,
  0xb2f4b448,0x31602fa5,0x36a437fe,0xb53ab389,0xafa5b160,0x344832f4,0x3389353a,0xb7feb6a4,0xa617ac93,0x35f6351c,0x2a16308d,0xb93cb8a3,
};
__device__ __align__(128) const uint32_t c_img[2560] = {
  0x326d31ed,0x333b32dd,0x33c33388,0x33fe33ea,0x33c331ed,0x31ed33c3,0xa8b22d64,0xb33bb0c4,0x33ea31ed,0xad64301d,0xb2ddb388,0x315fa8b2,
  0x32dd31ed,0xb3feabc6,0x326dad64,0xad64326d,0x30c431ed,0xaed7b2dd,0x2bc63388,0xa248b3ea,0x2bc631ed,0x315fb3c3,0xb3ea2d64,0x2ed730c4,
  0xa8b231ed,0x3388b01d,0x301db388,0xb1ed28b2,0xb01d31ed,0x22482bc6,0x30c4ad64,0x3388b26d,0x33ea33fe,0x338833c3,0x32dd333b,0x31ed326d,
  0xb2ddb3fe,0xa248b01d,0x326d2ed7,0x338833ea,0x30c433fe,0xb33babc6,0xabc6b33b,0x33fe30c4,0xabc6b3fe,0x31ed32dd,0xb3eaaed7,0x333ba8b2,
  0xa8b233fe,0x2d64b3c3,0xb01d333b,0x315fb26d,0x301db3fe,0xb3fe301d,0x30c42ed7,0x2d64b3ea,0xb26d33fe,0x2ed72bc6,0x33c3b33b,0xa248b0c4,
  0x33c3b3fe,0x315fb2dd,0x28b2aed7,0xaed728b2,0xb0c4b15f,0xaed7b01d,0xabc6ad64,0xa248a8b2,0xabc6b15f,0x315f2bc6,0x33ea3388,0x2ed7326d,
  0x28b2b15f,0x338832dd,0xb01d2d64,0xb1edb3ea,0x301db15f,0x224833c3,0xb0c4b388,0x338830c4,0x326db15f,0xb33b301d,0x33c3ad64,0xb3fe28b2,
  0x33c3b15f,0xb1edabc6,0xa8b23388,0x333bb26d,0x33eab15f,0x2d64b2dd,0xb2dd2d64,0xb15f33ea,0x32ddb15f,0x33feb3c3,0x326db388,0x2d64b0c4,
  0x28b22248,0x2d642bc6,0x301d2ed7,0x315f30c4,0xb01da248,0xb3feb2dd,0xb0c4b33b,0x2d64a8b2,0x326d2248,0x2ed733c3,0xb3c3aed7,0xa248b26d,
  0xb3c3a248,0x315fb01d,0xa8b2333b,0xaed7b3ea,0x33ea2248,0xb388abc6,0x32dd2ed7,0xb1edb0c4,0xb2dda248,0x224832dd,0x326db33b,0xb38828b2,
  0x30c42248,0x333bb3c3,0xabc6aed7,0xb3fe326d,0xabc6a248,0xb1ed301d,0xb3ea333b,0xb33b33ea,0xb26d31ed,0xb33b32dd,0xb3c33388,0xb3fe33ea,
  0xb3c331ed,0xb1ed33c3,0x28b22d64,0x333bb0c4,0xb3ea31ed,0x2d64301d,0x32ddb388,0xb15fa8b2,0xb2dd31ed,0x33feabc6,0xb26dad64,0x2d64326d,
  0xb0c431ed,0x2ed7b2dd,0xabc63388,0x2248b3ea,0xabc631ed,0xb15fb3c3,0x33ea2d64,0xaed730c4,0x28b231ed,0xb388b01d,0xb01db388,0x31ed28b2,
  0x301d31ed,0xa2482bc6,0xb0c4ad64,0xb388b26d,0xb3ea33fe,0xb38833c3,0xb2dd333b,0xb1ed326d,0x32ddb3fe,0x2248b01d,0xb26d2ed7,0xb38833ea,
  0xb0c433fe,0x333babc6,0x2bc6b33b,0xb3fe30c4,0x2bc6b3fe,0xb1ed32dd,0x33eaaed7,0xb33ba8b2,0x28b233fe,0xad64b3c3,0x301d333b,0xb15fb26d,
  0xb01db3fe,0x33fe301d,0xb0c42ed7,0xad64b3ea,0x326d33fe,0xaed72bc6,0xb3c3b33b,0x2248b0c4,0xb3c3b3fe,0xb15fb2dd,0xa8b2aed7,0x2ed728b2,
  0x30c4b15f,0x2ed7b01d,0x2bc6ad64,0x2248a8b2,0x2bc6b15f,0xb15f2bc6,0xb3ea3388,0xaed7326d,0xa8b2b15f,0xb38832dd,0x301d2d64,0x31edb3ea,
  0xb01db15f,0xa24833c3,0x30c4b388,0xb38830c4,0xb26db15f,0x333b301d,0xb3c3ad64,0x33fe28b2,0xb3c3b15f,0x31edabc6,0x28b23388,0xb33bb26d,
  0xb3eab15f,0xad64b2dd,0x32dd2d64,0x315f33ea,0xb2ddb15f,0xb3feb3c3,0xb26db388,0xad64b0c4,0xa8b22248,0xad642bc6,0xb01d2ed7,0xb15f30c4,
  0x301da248,0x33feb2dd,0x30c4b33b,0xad64a8b2,0xb26d2248,0xaed733c3,0x33c3aed7,0x2248b26d,0x33c3a248,0xb15fb01d,0x28b2333b,0x2ed7b3ea,
  0xb3ea2248,0x3388abc6,0xb2dd2ed7,0x31edb0c4,0x32dda248,0xa24832dd,0xb26db33b,0x338828b2,0xb0c42248,0xb33bb3c3,0x2bc6aed7,0x33fe326d,
  0x2bc6a248,0x31ed301d,0x33ea333b,0x333b33ea,0x30c4315f,0x2ed7301d,0x2bc62d64,0x224828b2,0x2bc6315f,0xb15fabc6,0xb3eab388,0xaed7b26d,
  0xa8b2315f,0xb388b2dd,0x301dad64,0x31ed33ea,0xb01d315f,0xa248b3c3,0x30c43388,0xb388b0c4,0xb26d315f,0x333bb01d,0xb3c32d64,0x33fea8b2,
  0xb3c3315f,0x31ed2bc6,0x28b2b388,0xb33b326d,0xb3ea315f,0xad6432dd,0x32ddad64,0x315fb3ea,0xb2dd315f,0xb3fe33c3,0xb26d3388,0xad6430c4,
  0xa8b2a248,0xad64abc6,0xb01daed7,0xb15fb0c4,0x301d2248,0x33fe32dd,0x30c4333b,0xad6428b2,0xb26da248,0xaed7b3c3,0x33c32ed7,0x2248326d,
  0x33c32248,0xb15f301d,0x28b2b33b,0x2ed733ea,0xb3eaa248,0x33882bc6,0xb2ddaed7,0x31ed30c4,0x32dd2248,0xa248b2dd,0xb26d333b,0x3388a8b2,
  0xb0c4a248,0xb33b33c3,0x2bc62ed7,0x33feb26d,0x2bc62248,0x31edb01d,0x33eab33b,0x333bb3ea,0x326d31ed,0x333b32dd,0x33c33388,0x33fe33ea,
  0x33c331ed,0x31ed33c3,0xa8b22d64,0xb33bb0c4,0x33ea31ed,0xad64301d,0xb2ddb388,0x315fa8b2,0x32dd31ed,0xb3feabc6,0x326dad64,0xad64326d,
  0x30c431ed,0xaed7b2dd,0x2bc63388,0xa248b3ea,0x2bc631ed,0x315fb3c3,0xb3ea2d64,0x2ed730c4,0xa8b231ed,0x3388b01d,0x301db388,0xb1ed28b2,
  0xb01d31ed,0x22482bc6,0x30c4ad64,0x3388b26d,0x33ea33fe,0x338833c3,0x32dd333b,0x31ed326d,0xb2ddb3fe,0xa248b01d,0x326d2ed7,0x338833ea,
  0x30c433fe,0xb33babc6,0xabc6b33b,0x33fe30c4,0xabc6b3fe,0x31ed32dd,0xb3eaaed7,0x333ba8b2,0xa8b233fe,0x2d64b3c3,0xb01d333b,0x315fb26d,
  0x301db3fe,0xb3fe301d,0x30c42ed7,0x2d64b3ea,0xb26d33fe,0x2ed72bc6,0x33c3b33b,0xa248b0c4,0x33c3b3fe,0x315fb2dd,0x28b2aed7,0xaed728b2,
  0xb0c4315f,0xaed7301d,0xabc62d64,0xa24828b2,0xabc6315f,0x315fabc6,0x33eab388,0x2ed7b26d,0x28b2315f,0x3388b2dd,0xb01dad64,0xb1ed33ea,
  0x301d315f,0x2248b3c3,0xb0c43388,0x3388b0c4,0x326d315f,0xb33bb01d,0x33c32d64,0xb3fea8b2,0x33c3315f,0xb1ed2bc6,0xa8b2b388,0x333b326d,
  0x33ea315f,0x2d6432dd,0xb2ddad64,0xb15fb3ea,0x32dd315f,0x33fe33c3,0x326d3388,0x2d6430c4,0x28b2a248,0x2d64abc6,0x301daed7,0x315fb0c4,
  0xb01d2248,0xb3fe32dd,0xb0c4333b,0x2d6428b2,0x326da248,0x2ed7b3c3,0xb3c32ed7,0xa248326d,0xb3c32248,0x315f301d,0xa8b2b33b,0xaed733ea,
  0x33eaa248,0xb3882bc6,0x32ddaed7,0xb1ed30c4,0xb2dd2248,0x2248b2dd,0x326d333b,0xb388a8b2,0x30c4a248,0x333b33c3,0xabc62ed7,0xb3feb26d,
  0xabc62248,0xb1edb01d,0xb3eab33b,0xb33bb3ea,0xb26d31ed,0xb33b32dd,0xb3c33388,0xb3fe33ea,0xb3c331ed,0xb1ed33c3,0x28b22d64,0x333bb0c4,
  0xb3ea31ed,0x2d64301d,0x32ddb388,0xb15fa8b2,0xb2dd31ed,0x33feabc6,0xb26dad64,0x2d64326d,0xb0c431ed,0x2ed7b2dd,0xabc63388,0x2248b3ea,
  0xabc631ed,0xb15fb3c3,0x33ea2d64,0xaed730c4,0x28b231ed,0xb388b01d,0xb01db388,0x31ed28b2,0x301d31ed,0xa2482bc6,0xb0c4ad64,0xb388b26d,
  0xb3ea33fe,0xb38833c3,0xb2dd333b,0xb1ed326d,0x32ddb3fe,0x2248b01d,0xb26d2ed7,0xb38833ea,0xb0c433fe,0x333babc6,0x2bc6b33b,0xb3fe30c4,
  0x2bc6b3fe,0xb1ed32dd,0x33eaaed7,0xb33ba8b2,0x28b233fe,0xad64b3c3,0x301d333b,0xb15fb26d,0xb01db3fe,0x33fe301d,0xb0c42ed7,0xad64b3ea,
  0x326d33fe,0xaed72bc6,0xb3c3b33b,0x2248b0c4,0xb3c3b3fe,0xb15fb2dd,0xa8b2aed7,0x2ed728b2,0x29ed29ed,0x29ed29ed,0x29ed29ed,0x29ed29ed,
  0x2bc32a6d,0x2add2bea,0x23c628c4,0xa81da0b2,0x2bc32add,0xa3c6281d,0xabc3aadd,0x23c6a81d,0x29ed2b3b,0xabfea564,0x295fa6d7,0x1a482b88,
  0x25642b88,0xa564ab88,0x25642b88,0xa564ab88,0xa0b22bc3,0x2a6daadd,0xabea23c6,0x28c4281d,0xa8c42bea,0x2a6da0b2,0x28c4abea,0xaa6d20b2,
  0xab3b2bfe,0xa564295f,0x26d79a48,0x2b88a9ed,0x29ed29ed,0x29ed29ed,0x29ed29ed,0x29ed29ed,0xabc3aa6d,0xaaddabea,0xa3c6a8c4,0x281d20b2,
  0x2bc32add,0xa3c6281d,0xabc3aadd,0x23c6a81d,0xa9edab3b,0x2bfe2564,0xa95f26d7,0x9a48ab88,0x25642b88,0xa564ab88,0x25642b88,0xa564ab88,
  0x20b2abc3,0xaa6d2add,0x2beaa3c6,0xa8c4a81d,0xa8c42bea,0x2a6da0b2,0x28c4abea,0xaa6d20b2,0x2b3babfe,0x2564a95f,0xa6d71a48,0xab8829ed,
  0x295f295f,0x295f295f,0x295f295f,0x295f295f,0x23c628c4,0xa81da0b2,0xabc3aa6d,0xaaddabea,0xa3c6281d,0xabc3aadd,0x23c6a81d,0x2bc32add,
  0xa95f26d7,0x9a48ab88,0x29ed2b3b,0xabfea564,0xab882564,0x2b88a564,0xab882564,0x2b88a564,0xabea23c6,0x28c4281d,0x20b2abc3,0xaa6d2add,
  0xaa6d20b2,0xa8c42bea,0x2a6da0b2,0x28c4abea,0xa6d71a48,0xab8829ed,0xab3b2bfe,0xa564295f,0x295f295f,0x295f295f,0x295f295f,0x295f295f,
  0xa3c6a8c4,0x281d20b2,0x2bc32a6d,0x2add2bea,0xa3c6281d,0xabc3aadd,0x23c6a81d,0x2bc32add,0x295fa6d7,0x1a482b88,0xa9edab3b,0x2bfe2564,
  0xab882564,0x2b88a564,0xab882564,0x2b88a564,0x2beaa3c6,0xa8c4a81d,0xa0b22bc3,0x2a6daadd,0xaa6d20b2,0xa8c42bea,0x2a6da0b2,0x28c4abea,
  0x26d79a48,0x2b88a9ed,0x2b3babfe,0x2564a95f,0xabfe2bfe,0xabfe2bfe,0xabfe2bfe,0xabfe2bfe,0xaadd2bea,0xa3c628c4,0x281da0b2,0x2bc3aa6d,
  0xa81d2bc3,0x2adda3c6,0x281dabc3,0xaadd23c6,0x9a482b88,0x29edab3b,0xabfe2564,0x295f26d7,0x26d72b3b,0xa6d7ab3b,0x26d72b3b,0xa6d7ab3b,
  0x2a6d2add,0xabeaa3c6,0x28c4a81d,0x20b22bc3,0x2bea2a6d,0xa0b228c4,0xabeaaa6d,0x20b2a8c4,0x2b8829ed,0x2b3b2bfe,0x2564295f,0xa6d79a48,
  0xabfe2bfe,0xabfe2bfe,0xabfe2bfe,0xabfe2bfe,0x2addabea,0x23c6a8c4,0xa81d20b2,0xabc32a6d,0xa81d2bc3,0x2adda3c6,0x281dabc3,0xaadd23c6,
  0x1a48ab88,0xa9ed2b3b,0x2bfea564,0xa95fa6d7,0x26d72b3b,0xa6d7ab3b,0x26d72b3b,0xa6d7ab3b,0xaa6daadd,0x2bea23c6,0xa8c4281d,0xa0b2abc3,
  0x2bea2a6d,0xa0b228c4,0xabeaaa6d,0x20b2a8c4,0xab88a9ed,0xab3babfe,0xa564a95f,0x26d71a48,0x1a489a48,0x1a489a48,0x1a489a48,0x1a489a48,
  0x281da0b2,0x2bc3aa6d,0x2addabea,0x23c6a8c4,0x2adda3c6,0x281dabc3,0xaadd23c6,0xa81d2bc3,0x2bfea564,0xa95fa6d7,0x9a482b88,0x29edab3b,
  0x2b3ba6d7,0xab3b26d7,0x2b3ba6d7,0xab3b26d7,0x28c4a81d,0x20b22bc3,0xaa6daadd,0x2bea23c6,0x20b2a8c4,0x2bea2a6d,0xa0b228c4,0xabeaaa6d,
  0xa564a95f,0x26d71a48,0x2b8829ed,0x2b3b2bfe,0x1a489a48,0x1a489a48,0x1a489a48,0x1a489a48,0xa81d20b2,0xabc32a6d,0xaadd2bea,0xa3c628c4,
  0x2adda3c6,0x281dabc3,0xaadd23c6,0xa81d2bc3,0xabfe2564,0x295f26d7,0x1a48ab88,0xa9ed2b3b,0x2b3ba6d7,0xab3b26d7,0x2b3ba6d7,0xab3b26d7,
  0xa8c4281d,0xa0b2abc3,0x2a6d2add,0xabeaa3c6,0x20b2a8c4,0x2bea2a6d,0xa0b228c4,0xabeaaa6d,0x2564295f,0xa6d79a48,0xab88a9ed,0xab3babfe,
  0xa95fa95f,0xa95fa95f,0xa95fa95f,0xa95fa95f,0xa3c6a8c4,0x281d20b2,0x2bc32a6d,0x2add2bea,0x23c6a81d,0x2bc32add,0xa3c6281d,0xabc3aadd,
  0x295fa6d7,0x1a482b88,0xa9edab3b,0x2bfe2564,0x2b88a564,0xab882564,0x2b88a564,0xab882564,0x2beaa3c6,0xa8c4a81d,0xa0b22bc3,0x2a6daadd,
  0x2a6da0b2,0x28c4abea,0xaa6d20b2,0xa8c42bea,0x26d79a48,0x2b88a9ed,0x2b3babfe,0x2564a95f,0xa95fa95f,0xa95fa95f,0xa95fa95f,0xa95fa95f,
  0x23c628c4,0xa81da0b2,0xabc3aa6d,0xaaddabea,0x23c6a81d,0x2bc32add,0xa3c6281d,0xabc3aadd,0xa95f26d7,0x9a48ab88,0x29ed2b3b,0xabfea564,
  0x2b88a564,0xab882564,0x2b88a564,0xab882564,0xabea23c6,0x28c4281d,0x20b2abc3,0xaa6d2add,0x2a6da0b2,0x28c4abea,0xaa6d20b2,0xa8c42bea,
  0xa6d71a48,0xab8829ed,0xab3b2bfe,0xa564295f,0x29ed29ed,0x29ed29ed,0x29ed29ed,0x29ed29ed,0x2bc32a6d,0x2add2bea,0x23c628c4,0xa81da0b2,
  0x2bc32add,0xa3c6281d,0xabc3aadd,0x23c6a81d,0x29ed2b3b,0xabfea564,0x295fa6d7,0x1a482b88,0x25642b88,0xa564ab88,0x25642b88,0xa564ab88,
  0xa0b22bc3,0x2a6daadd,0xabea23c6,0x28c4281d,0xa8c42bea,0x2a6da0b2,0x28c4abea,0xaa6d20b2,0xab3b2bfe,0xa564295f,0x26d79a48,0x2b88a9ed,
  0x29ed29ed,0x29ed29ed,0x29ed29ed,0x29ed29ed,0xabc3aa6d,0xaaddabea,0xa3c6a8c4,0x281d20b2,0x2bc32add,0xa3c6281d,0xabc3aadd,0x23c6a81d,
  0xa9edab3b,0x2bfe2564,0xa95f26d7,0x9a48ab88,0x25642b88,0xa564ab88,0x25642b88,0xa564ab88,0x20b2abc3,0xaa6d2add,0x2beaa3c6,0xa8c4a81d,
  0xa8c42bea,0x2a6da0b2,0x28c4abea,0xaa6d20b2,0x2b3babfe,0x2564a95f,0xa6d71a48,0xab8829ed,0x9a481a48,0x9a481a48,0x9a481a48,0x9a481a48,
  0xa81d20b2,0xabc32a6d,0xaadd2bea,0xa3c628c4,0xaadd23c6,0xa81d2bc3,0x2adda3c6,0x281dabc3,0xabfe2564,0x295f26d7,0x1a48ab88,0xa9ed2b3b,
  0xab3b26d7,0x2b3ba6d7,0xab3b26d7,0x2b3ba6d7,0xa8c4281d,0xa0b2abc3,0x2a6d2add,0xabeaa3c6,0xa0b228c4,0xabeaaa6d,0x20b2a8c4,0x2bea2a6d,
  0x2564295f,0xa6d79a48,0xab88a9ed,0xab3babfe,0x9a481a48,0x9a481a48,0x9a481a48,0x9a481a48,0x281da0b2,0x2bc3aa6d,0x2addabea,0x23c6a8c4,
  0xaadd23c6,0xa81d2bc3,0x2adda3c6,0x281dabc3,0x2bfea564,0xa95fa6d7,0x9a482b88,0x29edab3b,0xab3b26d7,0x2b3ba6d7,0xab3b26d7,0x2b3ba6d7,
  0x28c4a81d,0x20b22bc3,0xaa6daadd,0x2bea23c6,0xa0b228c4,0xabeaaa6d,0x20b2a8c4,0x2bea2a6d,0xa564a95f,0x26d71a48,0x2b8829ed,0x2b3b2bfe,
  0xabfe2bfe,0xabfe2bfe,0xabfe2bfe,0xabfe2bfe,0xaadd2bea,0xa3c628c4,0x281da0b2,0x2bc3aa6d,0xa81d2bc3,0x2adda3c6,0x281dabc3,0xaadd23c6,
  0x9a482b88,0x29edab3b,0xabfe2564,0x295f26d7,0x26d72b3b,0xa6d7ab3b,0x26d72b3b,0xa6d7ab3b,0x2a6d2add,0xabeaa3c6,0x28c4a81d,0x20b22bc3,
  0x2bea2a6d,0xa0b228c4,0xabeaaa6d,0x20b2a8c4,0x2b8829ed,0x2b3b2bfe,0x2564295f,0xa6d79a48,0xabfe2bfe,0xabfe2bfe,0xabfe2bfe,0xabfe2bfe,
  0x2addabea,0x23c6a8c4,0xa81d20b2,0xabc32a6d,0xa81d2bc3,0x2adda3c6,0x281dabc3,0xaadd23c6,0x1a48ab88,0xa9ed2b3b,0x2bfea564,0xa95fa6d7,
  0x26d72b3b,0xa6d7ab3b,0x26d72b3b,0xa6d7ab3b,0xaa6daadd,0x2bea23c6,0xa8c4281d,0xa0b2abc3,0x2bea2a6d,0xa0b228c4,0xabeaaa6d,0x20b2a8c4,
  0xab88a9ed,0xab3babfe,0xa564a95f,0x26d71a48,0x3bfb3bff,0x3be53bf2,0x3bbf3bd4,0x3b873ba5,0x3bd03bfb,0x3b013b7c,0x399d3a60,0x378538bc,
  0x35173b52,0xbbc9b7c8,0xb074ba9b,0x3bfe391b,0x319e3b27,0xbbf3b979,0x363cb80a,0x3a2d3bc5,0xba093986,0x3a7eb8f8,0xbae5385f,0x3b3db77a,
  0xbabd393c,0x3bb0b699,0xbc00305b,0x3ba730d7,0xbb2a35c8,0xb8353bb2,0x3a64b1e8,0x3962bbf7,0xba90350b,0xba413bff,0x3602340e,0x3bf6bad8,
  0xac6aa5e4,0xb122af59,0xb402b294,0xb56ab4b7,0xb2deac9c,0xb7bdb5a5,0xb9b3b8d6,0xbb10ba73,0xbb96b676,0xb359bafe,0x3bec3884,0x2a163a29,
  0xbbe0b72c,0x2f27b9d6,0x3b5e3ae8,0xb91633a2,0xb941b9c9,0x38ad3a45,0xb80fbab3,0x36d23b13,0xb850ba0d,0x346f3b4a,0x1fdbbbed,0xb4ab3be8,
  0x3721bb76,0xbace3463,0xb8d13bdd,0x39ebadfb,0x3894bb98,0xb8fd281f,0xbb6a3bbd,0x2e2d3825,0x3b3f3b65,0x3ae83b16,0x3a813ab6,0x3a0d3a49,
  0x3263356a,0xad972b43,0xb5dfb359,0xb8eeb7f3,0xa9b139aa,0xbbedba25,0x3340b889,0x3b983afb,0xbaa2aa16,0xb4cfbb8e,0x3c0038ad,0xb44b38e5,
  0xbb853625,0x3bbdb4c3,0xbbe432ad,0x3bfbaf8b,0xbaacb6d2,0x39243954,0xb65fbace,0x2fbd3bb8,0xb9661648,0xba603bf8,0x383a31cf,0x3b27bbb3,
  0x3219b9eb,0xbb1836f4,0xb9903be5,0x37dd3010,0xb6c6b61a,0xb80ab76f,0xb8a8b85a,0xb93cb8f3,0xbbd7bb87,0xbbf8bbfd,0xbb71bbc9,0xba4dbaf1,
  0xbbfeb9a6,0x305bb91f,0x3bcb3a97,0xb50b37d2,0xb87abbfe,0x3ba13546,0x24523a7e,0xbbb5ba54,0xb576bb63,0x340e3ba3,0xb13bbbd3,0x2c9c3bf2,
  0x386abb3d,0xba2139f8,0x3b57b835,0xbbf13432,0x39e7bc00,0xb8d6adc9,0xbacb3bde,0x372c3457,0x3bdab962,0x3764bb35,0xb9c03122,0xbaf73bef,
  0x398b39cd,0x38fd3946,0x386538b2,0x37853815,0xba85b9c9,0xbb92bb1e,0xbbfebbdd,0xbbc2bbf5,0xb66b3682,0xbb01bb94,0x387fb371,0x3a2d3beb,
  0xbac7bb76,0x3a00ad33,0x36bb3bd4,0xbbeab79b,0xbc0026ad,0x3bf32c38,0xbbd6b109,0x3ba733eb,0x3153bbff,0xb70a3b9e,0x396bba9b,0xbade390c,
  0xb5d4b5bc,0xbbb03b2c,0x32013830,0x3bf6ba67,0x3bccbb52,0x2c06b92e,0xbb83385f,0xb8c73bab,0xb9c5b982,0xba41ba04,0xbab0ba7a,0xbb10bae1,
  0xb8a3b986,0xb52fb74e,0xa94db1e8,0x33d32e91,0xbb54bb4f,0x37bdb523,0x3a9e3bc8,0xb916308d,0x3840b5c8,0x394a3bf9,0xbb42b294,0xb0a6bb0a,
  0x251bbbff,0xaf273bfc,0x327cbbe6,0xb4ab3bc0,0x3be325e4,0xbb2fb4e7,0x39e33884,0xb81aba35,0x3b73bb78,0xb46fb715,0xbbdc3ad1,0x2e2d38cc,
  0x33283676,0x3bfcba19,0x3581bab3,0xba6b3493,0x363136dd,0x34cf3581,0x32c6341a,0x2fbd3153,0xbae1bb65,0xb970ba39,0xb715b889,0xb16cb4f3,
  0xb9a12a7a,0xb924bbfe,0x3a933042,0x37dd3bcc,0x308db9aa,0x3b453b07,0xb94632ad,0xb845bbfa,0xbb68b55e,0x3b1836bb,0xbabab805,0x3a4d38a3,
  0x3bc0b625,0xbbfe2ec3,0x3b9431cf,0xba89b742,0x9cb6b95d,0xbbf8396b,0xb1b63a5c,0x3bb5b840,0x38cc9648,0x3b81bbac,0xac38b85a,0xbbce3933,
  0xbb60bb3a,0xbba1bb83,0xbbd2bbbc,0xbbf1bbe3,0x3815361a,0x39df3907,0x3b2c3a97,0x3be23b9c,0xb9afbbfd,0x3a21294d,0x388e3bee,0xbaf7b328,
  0x3beb39a6,0xb6af37a6,0xba04bbd3,0x3ac42d00,0x360ebb89,0xb7643b42,0x3855baeb,0xb8ee3a85,0x33eb3b63,0x28e8bbf5,0xb5233bde,0x389ebb21,
  0x3c00b9f0,0x2d97b9e3,0xbbdf38db,0xb44b3ac7,0xba673c00,0x358d3487,0x3bfcbab6,0x330fba15,0x3b7a3bf1,0x394a3a93,0x33893764,0xb3d39cb6,
  0x3afb3be2,0x35eb3946,0xb4c328e8,0xbaa9b8cc,0x27763af7,0xbb2fbaba,0x3a76ad97,0x30a63b60,0xaf8b3ac4,0xb994bb94,0x3bf8358d,0xb8743815,
  0xbb4c38ee,0x3bfcb1b6,0xbad5b4cf,0x381a39af,0xbbb3389e,0x3b592c38,0xb76fb970,0xb24b3beb,0xb9d2344b,0xbb923bd2,0xb0f03924,0x3a6bb60e,
  0xb8f3330f,0xbc003b2c,0xb91f3b45,0x323233eb,0xb5b1afbd,0xba00b88e,0xbbc6bb18,0xbbc2bc00,0xb7d2b16c,0xbb6fba04,0xbba3bbfe,0xb86fba67,
  0xbbffb7dd,0x370ab855,0x38b73bf8,0xbbeab631,0xbbf2b845,0x39bcb523,0x2dc93b81,0xbaa5bae1,0xb68dba4d,0xac063bdf,0x382abba1,0xbade39a1,
  0xb457ba89,0xb6543bfc,0x3b16b9df,0xbbd8308d,0x397dbbb5,0xb52fb2c6,0xbbe73a21,0xb8c73b68,0x3a49bbce,0x2311b715,0xba2536af,0xbbd93bc0,
  0xb958b785,0xbb81ba9e,0xbbefbbf3,0xba89bb73,0xbbf7bbc2,0xb9b8bb42,0xaf59b70a,0x384a3328,0xbb8bba2d,0x39dfb27c,0x34263bb0,0xbbceb98b,
  0xb4b7bbea,0x3b6c39e3,0xbafe2c06,0x3185ba85,0xaadebba7,0xb6af3bdc,0x3a58ba41,0xbbe2366b,0x3a29bade,0xbc003581,0x3a45352f,0xb2f7bac7,
  0x3b37bbf6,0x28e8b865,0xbaee37bd,0xbac43c00,0x3b13b8c7,0x3b5cbbfe,0x3463b94a,0xb8993153,0xb9f4bb10,0xb58db87f,0x3029af27,0x389e35d4,
  0x2dfbb3d3,0x399936bb,0x3bf23b2f,0x3ac13bcc,0x3552b916,0x39703bd6,0xbbbab46f,0x330fb9c5,0x3ba530a6,0xb5f7396b,0xb7c8bbfc,0x3be138a3,
  0x3bfdb4ab,0xbb45b201,0x38e038fd,0xb16cbb54,0x391b381a,0xa17fbb83,0xb8f83b92,0x3bcfb840,0x36e82e2d,0x3bfebab0,0x37febb01,0xb845251b,
  0xb77a3a6b,0x3648294d,0x3bb2ba00,0x3a8cbbe3,0xb742b93c,0x2311b340,0x37a6340e,0x3aa93966,0x3b963a4d,0x3b7f3c00,0x380f3a21,0xb0be3219,
  0x3933b50b,0x35eb3be4,0xbbf5b8d6,0x3874b6c6,0x39413bb5,0xbbffb65f,0x38d1b764,0x33ba3bd7,0x3b9c2c9c,0xb994b83a,0x34873ae8,0x324bbbfe,
  0xb7213bf1,0x3b47b990,0xbbbf2d97,0x38c1387a,0x2d00372c,0x3b59b8a8,0x3a39bbed,0xb232b576,0xbbfb3af7,0xb9743b71,0x307434cf,0x3adbb86a,
  0x3b213a0d,0x3c003bcb,0x3b073bbd,0x386f39e7,0x351738ee,0xb599a452,0xbae5b924,0xbbe9bbda,0x3a153b98,0xbb6fb13b,0x2ec3ba60,0x3aa53b3f,
  0xba09344b,0xa884bb57,0x3a643b18,0xbbc3b263,0xb4f33bfb,0x39bcbacb,0xbbac380a,0x3bd8a9b1,0xbb2aafbd,0x36a439c0,0x3402bbf8,0xba6f3aa2,
  0xbbfa3b27,0xb6543a81,0x3907b05b,0x3bd9bb85,0x2c6ab7dd,0xb9da35df,0xbbec3ba1,0xb8203aac,0x3bf53b87,0x3b6c3bec,0x392e3a7e,0x32f73721,
  0xb9e7b785,0xbbfcbb5e,0xba81bbb0,0xb43eb894,0x379b3bfe,0xbc00b80f,0x374eb835,0x38993bfb,0xbb3fba2d,0x3b329fdb,0xb3403a41,0xb8eabbd0,
  0xb90c3b3d,0x3b5cb8d1,0xbbf93122,0x3ac13517,0x29b1bba7,0xb94f3b6a,0x3be4b7bd,0xbaf4b19e,0xbbab3962,0xb9993bbf,0x34e73359,0x3be1ba09,
  0x3b85bbf6,0x353ab99d,0xb83a2f27,0xbbf03abd,0x2e91356a,0xb5f7b074,0xba19b8ad,0xbbcfbb2a,0xb966bb10,0xaba7b63c,0x38a8346f,0x3bb73a90,
  0xbb0aaa16,0xa17fbae5,0x3b1e3ace,0xba8c2c6a,0x36c6b916,0x36ff3c00,0xbbcbb8fd,0x3a50b2de,0xba35b6d2,0x36483a64,0x2d33bbe5,0xb84a3b96,
  0x3bfeb4ab,0xb9fcb602,0x313b3b01,0x37e8bbe0,0x3493b9eb,0xb9b83402,0xbb9e3bc9,0xb1853941,0x35762e2d,0x3b90b9b3,0x3acbbbf3,0x2fefb850,
  0x3a543bcf,0x2884374e,0xb9f8b648,0xbbe9bbab,0x398b3bb7,0xb4db3340,0xbbdcb9fc,0xb911bb85,0xb4323a8c,0xb6a4bbf9,0x3b3539b8,0xbbc3ae91,
  0xb66b3a50,0xad65bbe4,0x38653b90,0xbb0db966,0xbbef384a,0x39da34e7,0x2b43bb6c,0xba6f3b0a,0xbc0037e8,0x3759383a,0x387fbbfc,0xbbf636c6,
  0xb7f33185,0xbb7f3a19,0xbb8e3c00,0xb8203a35,0xb5d42fef,0xba1d38a8,0xbbd63b32,0xbba93bfe,0xb8e5b2f7,0xbbffbb1e,0xb954bb5c,0x30beb493,
  0xb9c5b43e,0xbb9fbbcb,0xb201b94f,0x3a313576,0xbbb8b899,0x3b47ad33,0xb6f43999,0xb3babbf5,0xbb54b8ea,0x3bf9313b,0xbab0353a,0x3790b9e7,
  0xb010bac1,0xb9743b9e,0x3bfdb5f7,0xb8c1b79b,0x251bbaf4,0xbb1b3acb,0x3a9e2ba7,0x2e5fbb3f,0x3af1bbe1,0x3599b92e,0xb546a17f,0xbadb390c,
  0x3b73bbf0,0x3929ba81,0x327cb6ff,0xb49f29b1,0xb825baa9,0x353aaec3,0x3b7c3994,0x3af43bfa,0x360eb0be,0x3bf43a64,0x388e3b47,0xb7372c6a,
  0x38bcb874,0x2ba73bac,0xb979bb59,0x3bf03742,0x3c0033ba,0xbb043402,0x3855b974,0xacce3b96,0x3bc5b24b,0xb6ffb907,0xb6993c00,0x3bb7b933,
  0x363138c1,0x3902bbec,0xbbdf3599,0x34ff3941,0x30d73232,0x39fcb7a6,0x3bffbb6f,0x3a50bb9c,0xb9a13adb,0xb47b380f,0x32c62884,0x3937b721,
  0x3ad8386f,0x3b903bf5,0x35a539bc,0xb7e8ad00,0x3b683be9,0x2ef538d1,0xba93b6a4,0xbb24bbfb,0x3a733aa5,0xbbfcb487,0x39d6b654,0xafef3b21,
  0x1cb63bc3,0xb7b2bbbf,0x3aba39da,0xbbfab517,0xb3a23bd8,0x3b32ba39,0xbb4a2311,0x343e3a15,0xbb603a6f,0x3a3d3074,0x31b6bb7f,0xbb9a3a09,
  0xbbe83bd9,0xb94f3b07,0xa81f35eb,0x38eab4f3,0xb9af3820,0xbbae3ae5,0xbbd23bff,0xba113b2a,0x319e389e,0xb929b426,0xbc00bb45,0xb911bb37,
  0xbbffbac1,0xb805bafe,0x382a217f,0x3bfd3b13,0xbabd330f,0x34dbba58,0x36023bfe,0xbb0db9f4,0xb68dbbe1,0x3a5c3a45,0xbbe7b648,0x3b89adfb,
  0xba90b16c,0x2d653aee,0x39b3bb81,0xbbf63552,0x397dbbcf,0xbbbc3463,0x338939b8,0x39f0bba5,0x32deb845,0xb7593029,0xbb5e39df,0xbba93bfd,
  0x3b7aba8c,0x3beebbf2,0x3a76bb6c,0x36ddb91b,0xbbe0ba89,0xba1dbbba,0x1fdbb6af,0x3a3136e8,0xa776b84a,0x3aeb37c8,0x3ad53c00,0xaa7a377a,
  0xb850bbce,0x3b9f38e0,0xbb6a28e8,0x3790b958,0x3b4cb185,0xb8db38f8,0x30f0bb5c,0x355e3bf7,0x3894bbe2,0xbbf937fe,0x399d358d,0x2e5fbb8b,
  0x39d232f7,0x341abbb2,0xbbc63999,0x395d34b7,0x3bd0bac4,0x3b1bbbef,0x363cb970,0xb49faade,0xb5b13899,0x30422f59,0x38b7b5f7,0x3b3aba29,
  0x3219b3d3,0x3b0438b7,0x3b713bfc,0x34ff397d,0x36e83aa9,0xb8b2adc9,0xbbefbb59,0xb5bcba49,0x3bd730a6,0xb902382a,0xa452bb92,0x39373b7a,
  0xb9583874,0x3371bb16,0x34263c00,0xb982bafb,0x387a381a,0x347bbbe7,0xbb573a00,0x3b242776,0xbb8b324b,0x31093a25,0x3a58bb6f,0xbb4f2f8b,
  0xb86a3a6b,0x2ef53389,0x39c0b70a,0x3bfabb4c,0xaadeb232,0xb83034c3,0xbaee39bc,0xbbff3bb3,0x3bda3bc2,0x37b23a76,0xb5df2c06,0xbb9ab9d2,
  0xbb37b86f,0xba7abbf8,0x3029b654,0x3b7838f3,0x32633bea,0xba3dbad5,0x3c00352f,0xba1135b1,0xb9f4baa5,0x3bc8376f,0xbbba2311,0x39cdb7d2,
  0xbaa23ade,0x3baeb0f0,0xb65fb94a,0xb7373bff,0x3552bbd8,0xbbe6391f,0x38e035eb,0x3682bbf2,0xbaac38c7,0xbbf43bc6,0xb9903b2f,0xacce368d,
  0x3bfdbbd9,0x3ad1bba3,0x37feb994,0x26adb457,0x38a33b9a,0xb8dba452,0xbb83bbae,0x2a7ab86a,0x37423b78,0xbab6b426,0xb907bbe6,0x39aa2ade,
  0xb8403a11,0x341abb57,0x294d3bf4,0xb55ebbda,0xb93339cd,0x3889ba58,0xb7a63ad1,0x3625bb37,0xbbe33737,0x304239c0,0x3b42bb04,0xb95db263,
  0xbb9c3682,0xb2ad3aee,0x3bf5b8b2,0x1648b9f4,0xb3282cce,0xb80535df,0xb9e33902,0xbb3a3aa2,0xad0026ad,0xb1cf3029,0xb4873371,0xb61a3552,
  0xba85b4ff,0xba5cbc00,0x3581b47b,0x3bfd3aac,0xbb21b5bc,0xb85abbba,0x3a393109,0x39a63bfd,0xbac7b937,0x3bbc365f,0xbbfeaef5,0x3b89b219,
  0xba15b982,0x3a9738e0,0xbb07b830,0x3b6336e8,0x3153bb24,0xbbee3990,0x36bb37b2,0x39f0bbd7,0x34f3bb4f,0xbbd337fe,0xaec33a7a,0x3c00b958,
  0x3bccbbfa,0x3aebbb71,0x396bba3d,0x36ddb87a,0x3bfabbff,0x3bdebbef,0x3bacbbc8,0x3b65bb8b,0x3bc03911,0x38303b6a,0xb946ad65,0xbb4fbbd0,
  0x3a353bfd,0xb85f30f0,0xbb1ebbbc,0x35c8b5b1,0x38cc3b0d,0xba7ab99d,0x3b943759,0xbbffb19e,0xb4933b89,0x31e8bbc6,0xad333bee,0xa5e4bbff,
  0xb8153bf6,0x3bc8b63c,0xac38ba1d,0xbb783abd,0xbbf539f0,0x329438b7,0x3b9ebaeb,0xb676b68d,0xbbeb3ba9,0xbbe63c00,0xbb2c3b9f,0xb9cd3a90,
  0xb79b36dd,0xb884382a,0xb92e38db,0xb9c9397d,0x33eb3a31,0xbad1b602,0xba04bbf9,0x3682b2de,0xb90c2a7a,0xbab3bbe7,0x374eb41a,0x3b763b7a,
  0xba673790,0x38b2b9b3,0xb5233b1b,0x26adbbe0,0xbbabb55e,0x3bdd3389,0xbbf9b042,0x3bff2776,0xbae12e5f,0xb3713b5e,0x3bfcb929,0xb5bcb850,
  0xae91b95d,0xbbd43a76,0x34e73805,0x3b52bb4c,0x308db49f,0xb1091fdb,0xb71534db,0xb9823894,0x3b0abb3a,0x3a9bbad5,0x3a19ba5c,0x3986b9d2,
  0x2f8bb7e8,0x3bde3979,0x376f3b32,0xb9aab0d7,0x3bb83b24,0xb1223855,0xbbfdba3d,0xaa16b9a1,0x3bb3afef,0xbab63699,0x391fb94f,0xb6253ad8,
  0x30103bfa,0xb359bbdf,0x35463bae,0xb6d2bb68,0x38f3343e,0x3889bbff,0xbba3353a,0x96483a73,0xbaf13b9a,0x38ad32c6,0x39f8bbf4,0xb9eb9cb6,
  0xb7d238ea,0xb2ad35a5,0x2dc92ba7,0x361ab3a2,0xba543a11,0xbace3a93,0xbb353b04,0xbb873b60,0x3bf23af4,0x31cf39d6,0xbb16b6ff,0xb9a6bbe8,
  0xb4323737,0xbbe5baba,0x2b43b902,0x3bfe39af,0x34573bf0,0xb85abb4a,0x3a2539fc,0xbb63b825,0xbbef2cce,0x3bc9b1b6,0xbb8e347b,0x3b3db60e,
  0xba493bb7,0x3a97a81f,0x34c3bb90,0xbc0038bc,0xb7f3b4ff,0xba7e3bd2,0x39542ef5,0x3962bc00,0xbafb3a50,0xbbd33b7c,0xbbf83bfc,0xbb653bc5,
  0x38e5b937,0x3835b88e,0x36f4b7b2,0x356ab631,0xbb13bbe9,0x31e8b6f4,0x3bf239da,0x36763af1,0x3be83911,0x340e3ab0,0xbb7cb759,0xb72cbb73,
  0x2dfbbbc3,0x32943bfd,0xb7c8bb7f,0x39c93a54,0x38253b0d,0xb8d6ba9e,0x39793a1d,0xba0db98b,0x3ba5ba6f,0xb884b546,0xb8f83bff,0x3b76b432,
  0xb8bc3bf6,0x3ae8b27c,0x3699bb9f,0xbb98366b,0x391bb820,0x3ab3b9f8,0x3bb2bb47,0x3bffbbef,0xbbc53ba9,0xbbed3bdc,0xbbff3bf9,0xbbfb3c00,
  0x377ab0be,0x3bdd3b35,0x2f593974,0xbb52b7f3,0x30d73a31,0xbbbdb865,0xb5a5bb1b,0x3b2735d4,0x3bf733ba,0xbbd42b43,0x3afeb599,0xb98638e5,
  0xbad83790,0x3a60b87f,0xb9d63929,0x393cb9c5,0x34b738c1,0x3a9bbb8e,0xba45a884,0xb5c83bb8,0xba732e5f,0xb80a3bd6,0x3b4ab4db,0x350bbb54,
  0xba293adb,0xb85f3954,0xb46336a4,0x25e43010,0x33a2b49f,0x305bb201,0x281fad65,0xac9c251b,0x3f803f80,0x3f803f80,0x3f803f80,0x3f803f80,
  0x3f803f80,0x3f803f80,0x3f803f80,0x3f803f80,0x3f803f80,0x3f803f80,0x3f803f80,0x3f803f80,0x3f803f80,0x3f803f80,0x3f803f80,0x3f803f80,
  0x3f803f80,0x3f803f80,0x3f803f80,0x3f803f80,0x3f803f80,0x3f803f80,0x3f803f80,0x3f803f80,0x3f803f80,0x3f803f80,0x3f803f80,0x3f803f80,
  0x3f803f80,0x3f803f80,0x3f803f80,0x3f803f80,0x3f803f80,0x3f803f80,0x3f803f80,0x3f803f80,0x3f803f80,0x3f803f80,0x3f803f80,0x3f803f80,
  0x3f803f80,0x3f803f80,0x3f803f80,0x3f803f80,0x3f803f80,0x3f803f80,0x3f803f80,0x3f803f80,0x3f803f80,0x3f803f80,0x3f803f80,0x3f803f80,
  0x3f803f80,0x3f803f80,0x3f803f80,0x3f803f80,0x3f803f80,0x3f803f80,0x3f803f80,0x3f803f80,0x3f803f80,0x3f803f80,0x3f803f80,0x3f803f80,
  0x3f803f80,0x3f803f80,0x3f803f80,0x3f803f80,0x3f803f80,0x3f803f80,0x3f803f80,0x3f803f80,0x3f803f80,0x3f803f80,0x3f803f80,0x3f803f80,
  0x3f803f80,0x3f803f80,0x3f803f80,0x3f803f80,0x3f803f80,0x3f803f80,0x3f803f80,0x3f803f80,0x3f803f80,0x3f803f80,0x3f803f80,0x3f803f80,
  0x3f803f80,0x3f803f80,0x3f803f80,0x3f803f80,0x3f803f80,0x3f803f80,0x3f803f80,0x3f803f80,0x3f803f80,0x3f803f80,0x3f803f80,0x3f803f80,
  0x3f803f80,0x3f803f80,0x3f803f80,0x3f803f80,0x3f803f80,0x3f803f80,0x3f803f80,0x3f803f80,0x3f803f80,0x3f803f80,0x3f803f80,0x3f803f80,
  0x3f803f80,0x3f803f80,0x3f803f80,0x3f803f80,0x3f803f80,0x3f803f80,0x3f803f80,0x3f803f80,0x3f803f80,0x3f803f80,0x3f803f80,0x3f803f80,
  0x3f803f80,0x3f803f80,0x3f803f80,0x3f803f80,0x3f803f80,0x3f803f80,0x3f803f80,0x3f803f80,0x3f803f80,0x3f803f80,0x3f803f80,0x3f803f80,
  0x3f803f80,0x3f803f80,0x3f803f80,0x3f803f80,0x3f803f80,0x3f803f80,0x3f803f80,0x3f803f80,0x3f803f80,0x3f803f80,0x3f803f80,0x3f803f80,
  0x3f803f80,0x3f803f80,0x3f803f80,0x3f803f80,0x3f803f80,0x3f803f80,0x3f803f80,0x3f803f80,0x3f803f80,0x3f803f80,0x3f803f80,0x3f803f80,
  0x3f803f80,0x3f803f80,0x3f803f80,0x3f803f80,0x3f803f80,0x3f803f80,0x3f803f80,0x3f803f80,0x3f803f80,0x3f803f80,0x3f803f80,0x3f803f80,
  0x3f803f80,0x3f803f80,0x3f803f80,0x3f803f80,0x3f803f80,0x3f803f80,0x3f803f80,0x3f803f80,0x3f803f80,0x3f803f80,0x3f803f80,0x3f803f80,
  0x3f803f80,0x3f803f80,0x3f803f80,0x3f803f80,0x3f803f80,0x3f803f80,0x3f803f80,0x3f803f80,0x3f803f80,0x3f803f80,0x3f803f80,0x3f803f80,
  0x3f803f80,0x3f803f80,0x3f803f80,0x3f803f80,0x3f803f80,0x3f803f80,0x3f803f80,0x3f803f80,0x3f803f80,0x3f803f80,0x3f803f80,0x3f803f80,
  0x3f803f80,0x3f803f80,0x3f803f80,0x3f803f80,0x3f803f80,0x3f803f80,0x3f803f80,0x3f803f80,0x3f803f80,0x3f803f80,0x3f803f80,0x3f803f80,
  0x3f803f80,0x3f803f80,0x3f803f80,0x3f803f80,0x3f803f80,0x3f803f80,0x3f803f80,0x3f803f80,0x3f803f80,0x3f803f80,0x3f803f80,0x3f803f80,
  0x3f803f80,0x3f803f80,0x3f803f80,0x3f803f80,0x3f803f80,0x3f803f80,0x3f803f80,0x3f803f80,0x3f803f80,0x3f803f80,0x3f803f80,0x3f803f80,
  0x3f803f80,0x3f803f80,0x3f803f80,0x3f803f80,0x3f803f80,0x3f803f80,0x3f803f80,0x3f803f80,0x3f803f80,0x3f803f80,0x3f803f80,0x3f803f80,
  0x3f803f80,0x3f803f80,0x3f803f80,0x3f803f80,0x3f803f80,0x3f803f80,0x3f803f80,0x3f803f80,0x3f803f80,0x3f803f80,0x3f803f80,0x3f803f80,
  0x3f803f80,0x3f803f80,0x3f803f80,0x3f803f80,0x3f803f80,0x3f803f80,0x3f803f80,0x3f803f80,0x3f803f80,0x3f803f80,0x3f803f80,0x3f803f80,
  0x3f803f80,0x3f803f80,0x3f803f80,0x3f803f80,0x3f803f80,0x3f803f80,0x3f803f80,0x3f803f80,0x3f803f80,0x3f803f80,0x3f803f80,0x3f803f80,
  0x3f803f80,0x3f803f80,0x3f803f80,0x3f803f80,0x3f803f80,0x3f803f80,0x3f803f80,0x3f803f80,0x3f803f80,0x3f803f80,0x3f803f80,0x3f803f80,
  0x3f803f80,0x3f803f80,0x3f803f80,0x3f803f80,0x3f803f80,0x3f803f80,0x3f803f80,0x3f803f80,0x3f803f80,0x3f803f80,0x3f803f80,0x3f803f80,
  0x3f803f80,0x3f803f80,0x3f803f80,0x3f803f80,0x3f803f80,0x3f803f80,0x3f803f80,0x3f803f80,0x3f803f80,0x3f803f80,0x3f803f80,0x3f803f80,
  0x3f803f80,0x3f803f80,0x3f803f80,0x3f803f80,0x3f803f80,0x3f803f80,0x3f803f80,0x3f803f80,0x3f803f80,0x3f803f80,0x3f803f80,0x3f803f80,
  0x3f803f80,0x3f803f80,0x3f803f80,0x3f803f80,0x3f803f80,0x3f803f80,0x3f803f80,0x3f803f80,0x3f803f80,0x3f803f80,0x3f803f80,0x3f803f80,
  0x3f803f80,0x3f803f80,0x3f803f80,0x3f803f80,0x3f803f80,0x3f803f80,0x3f803f80,0x3f803f80,0x3f803f80,0x3f803f80,0x3f803f80,0x3f803f80,
  0x3f803f80,0x3f803f80,0x3f803f80,0x3f803f80,0x3f803f80,0x3f803f80,0x3f803f80,0x3f803f80,0x3f803f80,0x3f803f80,0x3f803f80,0x3f803f80,
  0x3f803f80,0x3f803f80,0x3f803f80,0x3f803f80,0x3f803f80,0x3f803f80,0x3f803f80,0x3f803f80,0x3f803f80,0x3f803f80,0x3f803f80,0x3f803f80,
  0x3f803f80,0x3f803f80,0x3f803f80,0x3f803f80,0x3f803f80,0x3f803f80,0x3f803f80,0x3f803f80,0x3f803f80,0x3f803f80,0x3f803f80,0x3f803f80,
  0x3f803f80,0x3f803f80,0x3f803f80,0x3f803f80,0x3f803f80,0x3f803f80,0x3f803f80,0x3f803f80,0x3f803f80,0x3f803f80,0x3f803f80,0x3f803f80,
  0x3f803f80,0x3f803f80,0x3f803f80,0x3f803f80,0x3f803f80,0x3f803f80,0x3f803f80,0x3f803f80,0x3f803f80,0x3f803f80,0x3f803f80,0x3f803f80,
  0x3f803f80,0x3f803f80,0x3f803f80,0x3f803f80,0x3f803f80,0x3f803f80,0x3f803f80,0x3f803f80,0x3f803f80,0x3f803f80,0x3f803f80,0x3f803f80,
  0x3f803f80,0x3f803f80,0x3f803f80,0x3f803f80,0x3f803f80,0x3f803f80,0x3f803f80,0x3f803f80,0x3f803f80,0x3f803f80,0x3f803f80,0x3f803f80,
  0x3f803f80,0x3f803f80,0x3f803f80,0x3f803f80,0x3f803f80,0x3f803f80,0x3f803f80,0x3f803f80,0x3f803f80,0x3f803f80,0x3f803f80,0x3f803f80,
  0x3f803f80,0x3f803f80,0x3f803f80,0x3f803f80,0x3f803f80,0x3f803f80,0x3f803f80,0x3f803f80,0x3f803f80,0x3f803f80,0x3f803f80,0x3f803f80,
  0x3f803f80,0x3f803f80,0x3f803f80,0x3f803f80,0x3f803f80,0x3f803f80,0x3f803f80,0x3f803f80,0x3f803f80,0x3f803f80,0x3f803f80,0x3f803f80,
  0x3f803f80,0x3f803f80,0x3f803f80,0x3f803f80,0x3f803f80,0x3f803f80,0x3f803f80,0x3f803f80,0x3f803f80,0x3f803f80,0x3f803f80,0x3f803f80,
  0x3f803f80,0x3f803f80,0x3f803f80,0x3f803f80,0x3f803f80,0x3f803f80,0x3f803f80,0x3f803f80,0x3f803f80,0x3f803f80,0x3f803f80,0x3f803f80,
  0x3f803f80,0x3f803f80,0x3f803f80,0x3f803f80,
};

__device__ __align__(128) float    g_part[16][8][2176];
__device__ __align__(128) float    g_kv[16][2176];
constexpr int OBLK = 16 * 1024 + 32;
__device__ __align__(128) uint4    g_o[16 * OBLK];
#define GSTAMP(role, i) do {} while (0)
#define STAMP(role, i) do {} while (0)
#define PDUMP(role) do {} while (0)
#define PROF_SMEM 0

constexpr int STAGE_BYTES = 57344;
constexpr int OFF_H = 4 * 16384, OFF_VP = 9 * 16384, OFF_SPARE = 10 * 16384;
constexpr int OFF_XT = 172032, XT_STRIDE = 4112;
constexpr int OFF_BAR = 204928, OFF_EPOCH = OFF_BAR + 640, OFF_EX = OFF_BAR + 656, OFF_D = OFF_BAR + 672, OFF_SCALE = OFF_BAR + 704;
constexpr int OFF_F2F = 205824, OFF_F2I = 207872, OFF_F4 = 209920, OFF_ONES = 214016, OFF_KVB = 214016;
constexpr int OFF_STG = 219136, STG_STRIDE = 4352, SMEM_TOTAL = 232192 + PROF_SMEM;
enum { B_FULL1 = 0, B_EMPTY1 = 3, B_Q = 6, B_ODONE1 = 7, B_O1RDY = 8, B_H = 9, B_XRAW = 10, B_XT = 11, B_KV = 12, B_Y = 13,  B_AFREE = 15,
       B_STG = 18, B_ODONE = 24, B_XFREE = 25, B_FULL2 = 33, B_CONS2 = 49, B_SFREE = 14, B_KV1 = 61, B_OLOC = 60, B_PKRDY = 62, B_PKFREE = 64, B_H2 = 65, B_G1DONE = 66, B_COUNT = 67, B_FIRST = 67 };
constexpr uint64_t SLOT_A = 0x6859468594685948ull, SLOT_B = 0x7103271032710326ull;
constexpr int NPRE = 6, BEARLY = 3;
__host__ __device__ constexpr int bar_count(int i) {
  return i < B_EMPTY1 ? 1 : i < B_Q ? 4 : i == B_XT ? 4 : i == B_H ? 4 : (i == B_SFREE || i == B_G1DONE) ? 2 : i >= B_PKFREE ? 4 : i >= B_PKRDY ? 8 : i == B_Y ? 9
       : (i >= B_AFREE && i < B_STG) ? 16 : (i == B_ODONE || i == B_ODONE1) ? 8 : (i >= B_XFREE && i < B_FULL2) ? 4
       : i == B_KV1 ? 1 : i == B_OLOC ? 2 : i >= B_CONS2 ? 4 : (i >= B_FULL2 && i < B_FULL2 + NPRE) ? 2 : 1;
}
__host__ __device__ constexpr uint64_t bar_counts(int r) {
  uint64_t v = 0;
  for (int w = 0; w < 11; w++) v |= (uint64_t)(bar_count(1 + 11 * r + w) - 1) << (4 * w);
  return v;
}
constexpr uint32_t SW128 = 64 | (1u << 30);
constexpr int SPIN_LIMIT = 1 << 22;
#define SPLIT0 2
#define OLOC 1
#define PFD 3
#define PD1 700
#define PD2 450
#define QPF 6
#define BPACE 250
#define OCH 3
#define O1D 1
#define HOLD2 12
#define D1 100
#define TRICK 2
#define HSTART 1500
#define PACE 800

__device__ __forceinline__ uint32_t smem_u32(const void* p) { return (uint32_t)__cvta_generic_to_shared(p); }
__device__ __forceinline__ void wg_fence() { asm volatile("wgmma.fence.sync.aligned;" ::: "memory"); }
__device__ __forceinline__ void wg_commit() { asm volatile("wgmma.commit_group.sync.aligned;" ::: "memory"); }
template <int N> __device__ __forceinline__ void wg_wait() { asm volatile("wgmma.wait_group.sync.aligned %0;" ::"n"(N) : "memory"); }
template <int N> __device__ __forceinline__ void keep(float (&d)[N]) {
#pragma unroll
  for (int i = 0; i < N; i++) asm volatile("" : "+f"(d[i])::"memory");
}
__device__ __forceinline__ void mbar_init(uint32_t bar, int cnt) { asm volatile("mbarrier.init.shared::cta.b64 [%0], %1;" ::"r"(bar), "r"(cnt)); }
__device__ __forceinline__ void mbar_expect(uint32_t bar, int bytes) { asm volatile("mbarrier.arrive.expect_tx.shared::cta.b64 _, [%0], %1;" ::"r"(bar), "r"(bytes) : "memory"); }
__device__ __forceinline__ void mbar_arrive(uint32_t bar) { asm volatile("mbarrier.arrive.shared::cta.b64 _, [%0];" ::"r"(bar) : "memory"); }
__device__ __forceinline__ void mbar_arrive_cl(uint32_t bar, uint32_t cta) {
  asm volatile("{\n.reg .b32 r;\nmapa.shared::cluster.u32 r, %0, %1;\nmbarrier.arrive.shared::cluster.b64 _, [r];\n}\n" ::"r"(bar), "r"(cta) : "memory");
}
__device__ __forceinline__ void mbar_wait(uint32_t bar, uint32_t parity) {
  asm volatile("{\n.reg .pred p;\n.reg .u32 n;\nmov.u32 n, 0;\n"
               "W_%=:\nmbarrier.try_wait.parity.shared::cta.b64 p, [%0], %1;\n@p bra D_%=;\n"
               "add.u32 n, n, 1;\nsetp.lt.u32 p, n, %2;\n@p bra W_%=;\ntrap;\nD_%=:\n}\n" ::"r"(bar), "r"(parity), "n"(SPIN_LIMIT) : "memory");
}
__device__ __forceinline__ void fence_async() { asm volatile("fence.proxy.async.shared::cta;" ::: "memory"); }
__device__ __forceinline__ void bar_sync(int id) { asm volatile("bar.sync %0, 128;" ::"r"(id) : "memory"); }
__device__ __forceinline__ void tma2d(uint32_t dst, const CUtensorMap* m, int c0, int c1, uint32_t bar) {
  asm volatile("cp.async.bulk.tensor.2d.shared::cluster.global.mbarrier::complete_tx::bytes [%0], [%1, {%3, %4}], [%2];"
               ::"r"(dst), "l"(m), "r"(bar), "r"(c0), "r"(c1) : "memory");
}
__device__ __forceinline__ void tma2d_mc(uint32_t dst, const CUtensorMap* m, int c0, int c1, uint32_t bar) {
  asm volatile("cp.async.bulk.tensor.2d.shared::cluster.global.mbarrier::complete_tx::bytes.multicast::cluster [%0], [%1, {%3, %4}], [%2], %5;"
               ::"r"(dst), "l"(m), "r"(bar), "r"(c0), "r"(c1), "h"((uint16_t)3) : "memory");
}
__device__ __forceinline__ void tma3d(uint32_t dst, const CUtensorMap* m, int c0, int c1, int c2, uint32_t bar) {
  asm volatile("cp.async.bulk.tensor.3d.shared::cluster.global.mbarrier::complete_tx::bytes [%0], [%1, {%3, %4, %5}], [%2];"
               ::"r"(dst), "l"(m), "r"(bar), "r"(c0), "r"(c1), "r"(c2) : "memory");
}
__device__ __forceinline__ void tma4d(uint32_t dst, const CUtensorMap* m, int c0, int c1, int c2, int c3, uint32_t bar) {
  asm volatile("cp.async.bulk.tensor.4d.shared::cluster.global.mbarrier::complete_tx::bytes [%0], [%1, {%3, %4, %5, %6}], [%2];"
               ::"r"(dst), "l"(m), "r"(bar), "r"(c0), "r"(c1), "r"(c2), "r"(c3) : "memory");
}
__device__ __forceinline__ void bulk_ld(uint32_t dst, const void* src, int bytes, uint32_t bar) {
  asm volatile("cp.async.bulk.shared::cluster.global.mbarrier::complete_tx::bytes [%0], [%1], %2, [%3];" ::"r"(dst), "l"(src), "r"(bytes), "r"(bar) : "memory");
}
__device__ __forceinline__ void bulk_ld_mc(uint32_t dst, const void* src, int bytes, uint32_t bar) {
  asm volatile("cp.async.bulk.shared::cluster.global.mbarrier::complete_tx::bytes.multicast::cluster [%0], [%1], %2, [%3], %4;"
               ::"r"(dst), "l"(src), "r"(bytes), "r"(bar), "h"((uint16_t)3) : "memory");
}
__device__ __forceinline__ void tma2d_st(const CUtensorMap* m, uint32_t src, int c0, int c1) {
  asm volatile("cp.async.bulk.tensor.2d.global.shared::cta.bulk_group [%0, {%2, %3}], [%1];" ::"l"(m), "r"(src), "r"(c0), "r"(c1) : "memory");
}
__device__ __forceinline__ void ldsm4(uint32_t (&r)[4], uint32_t a) {
  asm volatile("ldmatrix.sync.aligned.m8n8.x4.shared.b16 {%0,%1,%2,%3}, [%4];" : "=r"(r[0]), "=r"(r[1]), "=r"(r[2]), "=r"(r[3]) : "r"(a) : "memory");
}
__device__ __forceinline__ void ldsm4t(uint32_t (&r)[4], uint32_t a) {
  asm volatile("ldmatrix.sync.aligned.m8n8.x4.trans.shared.b16 {%0,%1,%2,%3}, [%4];" : "=r"(r[0]), "=r"(r[1]), "=r"(r[2]), "=r"(r[3]) : "r"(a) : "memory");
}
__device__ __forceinline__ void stsm4(uint32_t a, uint32_t r0, uint32_t r1, uint32_t r2, uint32_t r3) {
  asm volatile("stmatrix.sync.aligned.m8n8.x4.shared.b16 [%0], {%1,%2,%3,%4};" ::"r"(a), "r"(r0), "r"(r1), "r"(r2), "r"(r3) : "memory");
}
__device__ __forceinline__ uint32_t pk2(float lo, float hi) { uint32_t r; asm("cvt.rn.bf16x2.f32 %0, %1, %2;" : "=r"(r) : "f"(hi), "f"(lo)); return r; }
__device__ __forceinline__ uint32_t hmul(uint32_t a, uint32_t b) { uint32_t r; asm("mul.rn.bf16x2 %0, %1, %2;" : "=r"(r) : "r"(a), "r"(b)); return r; }
__device__ __forceinline__ uint32_t hadd(uint32_t a, uint32_t b) { uint32_t r; asm("add.rn.bf16x2 %0, %1, %2;" : "=r"(r) : "r"(a), "r"(b)); return r; }
__device__ __forceinline__ uint32_t hmin(uint32_t a, uint32_t b) { uint32_t r; asm("min.bf16x2 %0, %1, %2;" : "=r"(r) : "r"(a), "r"(b)); return r; }
__device__ __forceinline__ uint32_t hmaxabs(uint32_t a, uint32_t b) { uint32_t r; asm("max.xorsign.abs.bf16x2 %0, %1, %2;" : "=r"(r) : "r"(a), "r"(b)); return r; }
__device__ __forceinline__ float ex2(float x) { float r; asm("ex2.approx.ftz.f32 %0, %1;" : "=f"(r) : "f"(x)); return r; }
__device__ __forceinline__ float rcp_fast(float x) { float r; asm("rcp.approx.ftz.f32 %0, %1;" : "=f"(r) : "f"(x)); return r; }
__device__ __forceinline__ uint32_t phi2(float lo, float hi) {
  uint32_t t;
  asm("cvt.rn.relu.bf16x2.f32 %0, %1, %2;" : "=r"(t) : "f"(hi), "f"(lo));
  const uint32_t e = pk2(ex2(lo * 1.4426950408889634f), ex2(hi * 1.4426950408889634f));
  return hadd(hadd(t, hmin(e, 0x3F803F80u)), 0x35863586u);
}
__device__ __forceinline__ bool opaque_true() { uint32_t v; asm volatile("mov.u32 %0, %%nctaid.y;" : "=r"(v)); return v != 0; }
__device__ __forceinline__ int norm_exp(uint32_t (&v)[32], float f0) {
  uint32_t m[4] = {hmaxabs(__float_as_uint(f0) >> 16, v[0]), v[1], v[2], v[3]};
#pragma unroll
  for (int i = 4; i < 32; i++) m[i & 3] = hmaxabs(m[i & 3], v[i]);
  m[0] = hmaxabs(hmaxabs(m[0], m[1]), hmaxabs(m[2], m[3]));
  const int e = min(max((int)(__reduce_max_sync(~0u, max(m[0] & 0x7FFFu, (m[0] >> 16) & 0x7FFFu)) >> 7), 1), 253);
  if (e > 141) {
#pragma unroll
    for (int i = 0; i < 32; i++) v[i] = hmul(v[i], 0x07000700u);
  }
  return e;
}
__device__ __forceinline__ void norm_cvt(uint32_t (&v)[32], float f0, int e) {
  const uint32_t sc = (e > 141 ? 255 - e : 142 - e) * 0x00800080u;
#pragma unroll
  for (int i = 0; i < 32; i++) {
    const uint32_t a = hmul(v[i], sc);
    v[i] = (a & 0x0FFF0FFFu) * 7 + a;
  }
  v[0] = __byte_perm(v[0], __half_as_ushort(__float2half_rn(f0 * __uint_as_float((254 - e) << 23))), 0x3254);
}
__device__ __forceinline__ void poll_ge(const unsigned* p, unsigned target) {
#pragma unroll 1
  for (int n = 0; n < SPIN_LIMIT; n++) {
    unsigned v;
    asm volatile("ld.relaxed.gpu.global.u32 %0, [%1];" : "=r"(v) : "l"(p) : "memory");
    if (__all_sync(~0u, (int)(v - target) >= 0)) { asm volatile("fence.acquire.gpu;" ::: "memory"); return; }
  }
  __trap();
}

__device__ __forceinline__ bool elect_one() {
  uint32_t p;
  asm volatile("{\n.reg .pred p;\nelect.sync _|p, 0xffffffff;\nselp.u32 %0, 1, 0, p;\n}\n" : "=r"(p));
  return p;
}
__device__ __forceinline__ uint4 ld_na4(const void* p) {
  uint4 v;
  asm volatile("ld.global.L1::no_allocate.v4.u32 {%0,%1,%2,%3}, [%4];" : "=r"(v.x), "=r"(v.y), "=r"(v.z), "=r"(v.w) : "l"(p) : "memory");
  return v;
}
__device__ __forceinline__ void st_cg4(void* p, uint4 v) {
  asm volatile("st.global.cg.v4.u32 [%0], {%1,%2,%3,%4};" ::"l"(p), "r"(v.x), "r"(v.y), "r"(v.z), "r"(v.w) : "memory");
}
__device__ __forceinline__ uint32_t mapa(uint32_t a, uint32_t cta) { uint32_t r; asm("mapa.shared::cluster.u32 %0, %1, %2;" : "=r"(r) : "r"(a), "r"(cta)); return r; }
__device__ __forceinline__ void st_async(uint32_t a, uint32_t v, uint32_t bar) {
  asm volatile("st.async.weak.shared::cluster.mbarrier::complete_tx::bytes.b32 [%0], %1, [%2];" ::"r"(a), "r"(v), "r"(bar) : "memory");
}
__device__ __forceinline__ void st_async4(uint32_t a, uint32_t x, uint32_t y, uint32_t z, uint32_t w, uint32_t bar) {
  asm volatile("st.async.weak.shared::cluster.mbarrier::complete_tx::bytes.v4.b32 [%0], {%1,%2,%3,%4}, [%5];" ::"r"(a), "r"(x), "r"(y), "r"(z), "r"(w), "r"(bar) : "memory");
}
__device__ __forceinline__ void tma3d_st(const CUtensorMap* m, uint32_t src, int c0, int c1, int c2) {
  asm volatile("cp.async.bulk.tensor.3d.global.shared::cta.bulk_group [%0, {%2, %3, %4}], [%1];" ::"l"(m), "r"(src), "r"(c0), "r"(c1), "r"(c2) : "memory");
}
__device__ __forceinline__ uint4 ld_rlx4(const void* p) {
  uint4 v;
  asm volatile("{\n.reg .b128 t;\n.reg .b64 a, b;\nld.relaxed.gpu.global.b128 t, [%4];\nmov.b128 {a, b}, t;\nmov.b64 {%0, %1}, a;\nmov.b64 {%2, %3}, b;\n}\n"
               : "=r"(v.x), "=r"(v.y), "=r"(v.z), "=r"(v.w) : "l"(p) : "memory");
  return v;
}
__device__ __forceinline__ void ld_stale4(uint4& v, const void* p, uint32_t tag) {
  asm volatile("{\n.reg .b128 t;\n.reg .b64 a, b;\n.reg .b32 x;\n.reg .pred p;\n"
               "lop3.b32 x, %0, %5, 1, 0x28;\nsetp.ne.u32 p, x, 0;\n"
               "mov.b64 a, {%0, %1};\nmov.b64 b, {%2, %3};\nmov.b128 t, {a, b};\n"
               "@p ld.relaxed.gpu.global.b128 t, [%4];\n"
               "mov.b128 {a, b}, t;\nmov.b64 {%0, %1}, a;\nmov.b64 {%2, %3}, b;\n}\n"
               : "+r"(v.x), "+r"(v.y), "+r"(v.z), "+r"(v.w) : "l"(p), "r"(tag) : "memory");
}
__device__ __forceinline__ void st_tag4(void* p, float a, float b, float c, float d, uint32_t tag) {
  asm volatile("{\n.reg .b128 t;\n.reg .b64 a, b;\nmov.b64 a, {%1, %2};\nmov.b64 b, {%3, %4};\nmov.b128 t, {a, b};\nst.relaxed.gpu.global.b128 [%0], t;\n}\n"
               ::"l"(p), "r"((__float_as_uint(a) & ~1u) | tag), "f"(b), "f"(c), "f"(d) : "memory");
}
__device__ __forceinline__ uint32_t stale8(const uint4 (&f)[8], uint32_t tag) {
  uint32_t r[4];
#pragma unroll
  for (int i = 0; i < 4; i++) asm("lop3.b32 %0, %1, %2, %3, 0x7E;" : "=r"(r[i]) : "r"(f[2 * i].x), "r"(f[2 * i + 1].x), "r"(tag));
  asm("lop3.b32 %0, %0, %1, %2, 0xFE;" : "+r"(r[0]) : "r"(r[1]), "r"(r[2]));
  return r[0] | r[3];
}

struct ConvC { uint32_t a1[2][4], wa[2], wb[2], sg; };
__device__ __forceinline__ uint64_t dsc(uint32_t lo, uint32_t hi) { return ((uint64_t)hi << 32) | lo; }
__device__ __forceinline__ uint32_t hfma(uint32_t a, uint32_t b, uint32_t c) { uint32_t r; asm("fma.rn.f16x2 %0, %1, %2, %3;" : "=r"(r) : "r"(a), "r"(b), "r"(c)); return r; }
__device__ __forceinline__ uint32_t hfnma(uint32_t a, uint32_t b, uint32_t c) { uint32_t r; asm("{.reg .b32 n; neg.f16x2 n, %1; fma.rn.f16x2 %0, n, %2, %3;}" : "=r"(r) : "r"(a), "r"(b), "r"(c)); return r; }
__device__ __forceinline__ uint32_t hmul16(uint32_t a, uint32_t b) { uint32_t r; asm("mul.rn.f16x2 %0, %1, %2;" : "=r"(r) : "r"(a), "r"(b)); return r; }
template <int N> __device__ __forceinline__ void keepu(uint32_t (&d)[N]) {
#pragma unroll
  for (int i = 0; i < N; i++) asm volatile("" : "+r"(d[i])::"memory");
}
__device__ __forceinline__ void conv_m1(const ConvC& K, uint32_t (&u)[16], uint32_t l) {
  wg_fence();
  wgmma_hrs_n64<1>(u, K.a1[0][0], K.a1[0][1], K.a1[0][2], K.a1[0][3], dsc(l, 32), 0);
  wgmma_hrs_n64<1>(u, K.a1[1][0], K.a1[1][1], K.a1[1][2], K.a1[1][3], dsc(l + 16, 32), 1);
  wg_commit();
}
__device__ __forceinline__ void conv_s2(const ConvC& K, uint32_t (&u)[16], uint32_t (&Z)[2][8], uint32_t dfl) {
  uint32_t fr[8], fi[8];
#pragma unroll
  for (int c = 0; c < 8; c++) {
    const uint32_t r = hfma(K.wa[c & 1], u[2 * c + 1], u[2 * c]);
    fi[c] = hfma(K.wb[c & 1], r, u[2 * c + 1]);
    fr[c] = hfma(K.wa[c & 1], fi[c], r);
  }
  wg_fence();
#pragma unroll
  for (int p = 0; p < 2; p++) {
    wgmma_hrs_n32<0>(Z[p], fr[4 * p], fr[4 * p + 2], fr[4 * p + 1], fr[4 * p + 3], dsc(dfl, 32), 0);
    wgmma_hrs_n32<0>(Z[p], fi[4 * p], fi[4 * p + 2], fi[4 * p + 1], fi[4 * p + 3], dsc(dfl + 16, 32), 1);
  }
  wg_commit();
}
__device__ __forceinline__ void conv_win(const ConvC& K, const uint32_t (&X)[2][8], uint32_t (&W)[2][8]) {
#pragma unroll
  for (int b = 0; b < 4; b++)
#pragma unroll
    for (int c = 0; c < 2; c++) {
      const uint32_t xr = X[b >> 1][2 * c + (b & 1)], xi = X[b >> 1][4 + 2 * c + (b & 1)];
      const int a = b ? b - 1 : 0;
      W[b >> 1][2 * c + (b & 1)] = b ? hfnma(K.sg, X[a >> 1][4 + 2 * c + (a & 1)], xr) : hmul16(xr, 0x3C003C00u);
      W[b >> 1][4 + 2 * c + (b & 1)] = b ? hfma(K.sg, X[a >> 1][2 * c + (a & 1)], xi) : hmul16(xi, 0x3C003C00u);
    }
}
template <int p>
__device__ __forceinline__ void conv_pw(uint32_t (&X)[2][8], uint32_t (&H)[2][8], uint32_t (&V)[8], uint32_t dil) {
  uint32_t pr[2][2], pi[2][2];
#pragma unroll
  for (int jj = 0; jj < 2; jj++)
#pragma unroll
    for (int c = 0; c < 2; c++) {
      const int j = 2 * p + jj;
      uint32_t sr = 0, si = 0;
#pragma unroll
      for (int a = 0; a <= j; a++) {
        const int b = j - a;
        const uint32_t hr = H[a >> 1][2 * c + (a & 1)], hi = H[a >> 1][4 + 2 * c + (a & 1)];
        const uint32_t xr = X[b >> 1][2 * c + (b & 1)], xi = X[b >> 1][4 + 2 * c + (b & 1)];
        sr = a == 0 ? hmul16(hr, xr) : hfma(hr, xr, sr);
        si = a == 0 ? hmul16(hr, xi) : hfma(hr, xi, si);
        sr = hfnma(hi, xi, sr);
        si = hfma(hi, xr, si);
      }
      pr[jj][c] = sr; pi[jj][c] = si;
    }
  wg_fence();
  wgmma_hrs_n32<0>(V, pr[0][0], pr[1][0], pr[0][1], pr[1][1], dsc(dil, 32), 0);
  wgmma_hrs_n32<0>(V, pi[0][0], pi[1][0], pi[0][1], pi[1][1], dsc(dil + 16, 32), 1);
  wg_commit();
}
template <int p>
__device__ __forceinline__ void conv_it(const ConvC& K, uint32_t (&V)[8], uint32_t vst) {
#pragma unroll
  for (int jj = 0; jj < 2; jj++) {
    uint32_t wr[2], wi[2];
#pragma unroll
    for (int c = 0; c < 2; c++) {
      const uint32_t r = hfnma(K.wa[c], V[4 + 2 * c + jj], V[2 * c + jj]);
      wi[c] = hfnma(K.wb[c], r, V[4 + 2 * c + jj]);
      wr[c] = hfnma(K.wa[c], wi[c], r);
    }
    stsm4(vst + (2 * p + jj) * 2048, wr[0], wr[1], wi[0], wi[1]);
  }
}
__device__ __forceinline__ void conv_m4(uint32_t (&y)[8], uint32_t (&a)[4][4], uint32_t d4l) {
  wg_fence();
  wgmma_hrs_n32<0>(y, a[0][0], a[0][1], a[0][2], a[0][3], dsc(d4l, 64), 0);
#pragma unroll
  for (int s = 1; s < 4; s++) wgmma_hrs_n32<0>(y, a[s][0], a[s][1], a[s][2], a[s][3], dsc(d4l + s * 16, 64), 1);
  wg_commit();
}

struct Params {
  CUtensorMap tmX0, tmW, tmX, tmWo, tmWo1, tmK, tmV, tmQ, tmOA, tmOB;
  const __nv_bfloat16 *shift_k, *h, *D, *x, *w, *wo, *q;
  float *part, *kv;
  uint4* o;
  const uint32_t *thr, *img;
};

__global__ void __cluster_dims__(2, 1, 1) __launch_bounds__(384, 1) fused_kernel(const __grid_constant__ Params P) {
  extern __shared__ __align__(1024) uint8_t smem[];
  const uint32_t sb = __shfl_sync(~0u, smem_u32(smem), 0);
  const uint32_t bars = sb + OFF_BAR;
  const int tid = threadIdx.x, lane = tid & 31;
  const int warp = __shfl_sync(~0u, tid >> 5, 0);
  const int rank = blockIdx.x & 1, cl = blockIdx.x >> 1;
  const unsigned c7 = cl + 6, g7 = (c7 * 37) >> 8;
  const int mb = cl < 4 ? 4 + cl : cl < 36 ? (cl - 4) >> 3 : g7 - 2;
  const int hq = cl < 4 ? 0 : cl < 36 ? (cl - 4) & 7 : 1 + c7 - 7 * g7;
  const int hp = 2 * hq + rank;
  const int rb = 2 * mb + (hq >> 2), cb = hq & 3;
#define BAR(i) (bars + 8 * (i))
#define OCNT(rb, hh) ((unsigned*)(P.o + (rb) * OBLK + 16 * 1024 + 8 * (hh)))
#define EPOCH (OCNT(rb, 2)[hp & 7])

  if (tid == 0) { STAMP(0, 0); GSTAMP(0, 30); }
  if (warp == 8) {
    if (elect_one()) {
      mbar_init(BAR(B_FULL1), 1);
      mbar_init(BAR(B_FIRST), 1);
      asm volatile("fence.mbarrier_init.release.cluster;" ::: "memory");
      mbar_expect(BAR(B_FIRST), STAGE_BYTES - 16384);
      tma2d(sb, &P.tmX0, 0, mb * 256, BAR(B_FIRST));
      tma2d(sb + 16384, &P.tmX0, 0, mb * 256 + 128, BAR(B_FIRST));
      tma3d(sb + 32768, &P.tmW, hp * 64, 0, 0, BAR(B_FIRST));
    }
    if (lane == 0) STAMP(3, 21);
  } else if (lane == 0) {
    const int wi = warp - (warp > 8);
#pragma unroll
    for (int r = 0; r < 6; r++)
      if (r < 5 || wi < B_COUNT - 56) mbar_init(BAR(1 + 11 * r + wi), ((uint32_t)(bar_counts(r) >> (4 * wi)) & 15) + 1);
    asm volatile("fence.mbarrier_init.release.cluster;" ::: "memory");
  }
  if (tid == 0) STAMP(2, 6);
  asm volatile("barrier.cluster.arrive.relaxed.aligned;\nbarrier.cluster.wait.aligned;" ::: "memory");
  if (warp == 8 && elect_one()) {
    mbar_expect(BAR(B_FULL1), 16384);
    tma2d_mc(sb + 8192 + rank * 16384, &P.tmX0, 0, mb * 256 + 64 + rank * 128, BAR(B_FULL1));
  }
  if (tid == 256) STAMP(2, 7);

  if (warp < 8) {
    asm volatile("setmaxnreg.inc.sync.aligned.u32 224;");
    const int wg = warp >> 2, w = warp & 3, g = lane >> 2, q = lane & 3, t = tid & 127;
    const bool elect = (t == 0);
    const uint32_t s16 = (sb & 0x3FFFF) >> 4;
    uint32_t pq[2][16], ux[16], uh[16], X[4][2][8], H[4][2][8];
    ConvC K;
    const uint32_t dfl = s16 + (OFF_F2F >> 4) + (8 << 16), dil = s16 + (OFF_F2I >> 4) + (8 << 16), d4l = s16 + (OFF_F4 >> 4) + (8 << 16);
    const uint32_t xl = s16 + (OFF_XT >> 4) + 4 * wg * (XT_STRIDE >> 4) + (8 << 16);
    const uint32_t hl = s16 + (OFF_H >> 4) + wg * 512 + (8 << 16);
    {
      float acc[2][96];
      if (SPLIT0) {
#pragma unroll
        for (int mt = 0; mt < 2; mt++) {
          mbar_wait(BAR(mt ? B_FULL1 : B_FIRST), 0);
          if (mt == 0 && elect) { STAMP(wg, 1); GSTAMP(wg, 26); }
          wg_fence();
#pragma unroll
          for (int ks = 0; ks < 4; ks++)
            wgmma_ss_n192<0, 1>(acc[mt], dsc(s16 + wg * 1024 + mt * 512 + (1 << 16) + ks * 2, SW128), dsc(s16 + 2048 + (512 << 16) + ks * 128, SW128), ks != 0);
        }
        wg_commit();
      }
      int st = SPLIT0 ? 1 : 0, ph = 0;
#pragma unroll 1
      for (int kb = SPLIT0 ? 1 : 0; kb < 14; kb++) {
        mbar_wait(BAR(B_FULL1 + st), ph);
        if (kb == 0 && elect) { STAMP(wg, 1); GSTAMP(wg, 26); }
        if (kb == 8 && elect) { STAMP(wg, 16); GSTAMP(wg, 25); }
        const uint32_t da = s16 + st * (STAGE_BYTES >> 4) + wg * 1024 + (1 << 16);
        const uint32_t db = s16 + st * (STAGE_BYTES >> 4) + 2048 + (512 << 16);
        wg_fence();
#pragma unroll
        for (int ks = 0; ks < 4; ks++) {
          wgmma_ss_n192<0, 1>(acc[0], dsc(da + ks * 2, SW128), dsc(db + ks * 128, SW128), (kb | ks) != 0);
          wgmma_ss_n192<0, 1>(acc[1], dsc(da + 512 + ks * 2, SW128), dsc(db + ks * 128, SW128), (kb | ks) != 0);
        }
        wg_commit();
        wg_wait<1>();
        if (kb > 0 && t < 2) mbar_arrive_cl(BAR(B_EMPTY1 + (st == 0 ? 2 : st - 1)), t);
        if (++st == 3) { st = 0; ph ^= 1; }
      }
#define TAIL_MMA(mt, stage) do { wg_fence(); _Pragma("unroll") for (int ks = 0; ks < 4; ks++) \
        wgmma_ss_n192<0, 1>(acc[mt], dsc(s16 + (stage) * (STAGE_BYTES >> 4) + wg * 1024 + (mt) * 512 + (1 << 16) + ks * 2, SW128), \
                            dsc(s16 + (stage) * (STAGE_BYTES >> 4) + 2048 + (512 << 16) + ks * 128, SW128), 1); wg_commit(); } while (0)
      mbar_wait(BAR(B_FULL1 + 2), 0);
      TAIL_MMA(0, 2);
      wg_wait<1>();
      if (elect) mbar_arrive(BAR(B_SFREE));
      mbar_wait(BAR(B_FULL1 + 0), 1);
      TAIL_MMA(0, 0);
      TAIL_MMA(1, 2);
      const uint32_t lrow = sb + wg * 16384 + (16 * w + 8 * ((lane >> 3) & 1) + (lane & 7)) * 128 + (((lane >> 4) ^ (lane & 7)) << 4);
#define E1K(mt, i) do { if (opaque_true()) { _Pragma("unroll") for (int j = (i); j < (i) + 2; j++) { \
          const float* a = &acc[mt][32 + 8 * j]; const float* b = a + 32; const uint32_t o = (lrow ^ (j * 32)) + (mt) * 8192; \
          stsm4(o + 2 * STAGE_BYTES, pk2(b[0], b[1]), pk2(b[2], b[3]), pk2(b[4], b[5]), pk2(b[6], b[7])); \
          stsm4(o, phi2(a[0], a[1]), phi2(a[2], a[3]), phi2(a[4], a[5]), phi2(a[6], a[7])); } } } while (0)
#define E1Q(mt) do { if (opaque_true()) { _Pragma("unroll") for (int i = 0; i < 16; i++) pq[mt][i] = phi2(acc[mt][2 * i], acc[mt][2 * i + 1]); } } while (0)
#define LOAD_K() do { const uint4* ct = (const uint4*)P.thr + t; \
        _Pragma("unroll") for (int s = 0; s < 2; s++) { const uint4 u = ld_na4(ct + s * 128); K.a1[s][0] = u.x; K.a1[s][1] = u.y; K.a1[s][2] = u.z; K.a1[s][3] = u.w; } \
        const uint4 u = ld_na4(ct + 2 * 128); K.wa[0] = u.x; K.wa[1] = u.y; K.wb[0] = u.z; K.wb[1] = u.w; \
        K.sg = (lane & 4) ? 0xBC00BC00u : 0x3C003C00u; } while (0)
#define PK_READY(mt) do { fence_async(); __syncwarp(); if (lane == 0) mbar_arrive(BAR(B_PKRDY + (mt))); } while (0)
      wg_wait<1>();
      keep(acc[0]);
      if (elect) STAMP(wg, 18);
      E1K(0, 0);
      TAIL_MMA(1, 0);
      E1K(0, 2);
      if (elect) STAMP(wg, 19);
      PK_READY(0);
      wg_wait<0>();
      keep(acc[1]);
      if (elect) mbar_arrive(BAR(B_G1DONE));
      asm volatile("setmaxnreg.dec.sync.aligned.u32 200;");
      if (elect) { STAMP(wg, 2); GSTAMP(wg, 27); }
      E1K(1, 0);
      if (elect) STAMP(wg, 20);
      E1K(1, 2);
      if (elect) STAMP(wg, 21);
      PK_READY(1);
      if (elect) STAMP(wg, 3);
      LOAD_K();
      if (elect) STAMP(wg, 4);
      E1Q(0);
      E1Q(1);
      if (elect) STAMP(wg, 17);
      mbar_wait(BAR(B_H), 0);
      conv_m1(K, ux, xl);
      conv_m1(K, uh, hl);
      wg_wait<1>(); keepu(ux);
      if (lane == 0) mbar_arrive_cl(BAR(B_XFREE + 4 * wg), rank ^ 1);
      conv_s2(K, ux, X[0], dfl);
      wg_wait<1>(); keepu(uh);
      conv_s2(K, uh, H[0], dfl);
    }
    if (elect) STAMP(wg, 5);
    {
      uint32_t vst = sb + wg * 8192 + w * 512 + lane * 16, vld = sb + wg * 8192 + w * 2048 + lane * 16;
      uint32_t ya = mapa(sb + OFF_XT + 4 * wg * XT_STRIDE + (2 * rank + (w & 1)) * 1024 + lane * 16, w >> 1);
      const uint32_t ybar = mapa(BAR(B_Y), w >> 1);
      asm volatile("" : "+r"(vst), "+r"(vld), "+r"(ya));
      uint32_t W[2][8], V0[8], V1[8], y[8], a[4][4];
      uint4 ov[4];
      uint4* const ot = P.o + (2 * mb + wg) * OBLK + hq * 1024 + (16 * w + g) * 8 + ((4 * rank + q) ^ g);
#define YOUT(i) do { if ((w >> 1) == rank) { \
          asm volatile("st.shared.v4.b32 [%0], {%1,%2,%3,%4};" ::"r"(ya + (i) * XT_STRIDE), "r"(y[0]), "r"(y[2]), "r"(y[4]), "r"(y[6]) : "memory"); \
          asm volatile("st.shared.v4.b32 [%0], {%1,%2,%3,%4};" ::"r"(ya + (i) * XT_STRIDE + 512), "r"(y[1]), "r"(y[3]), "r"(y[5]), "r"(y[7]) : "memory"); \
        } else { \
          mbar_wait(BAR(B_XFREE + 4 * wg + (i)), 0); \
          st_async4(ya + (i) * XT_STRIDE, y[0], y[2], y[4], y[6], ybar); \
          st_async4(ya + (i) * XT_STRIDE + 512, y[1], y[3], y[5], y[7], ybar); } } while (0)
      auto ocalc = [&](const int hh) {
        if (hh == 0) {
          if (elect) STAMP(wg, 8);
          mbar_wait(BAR(B_KV), 0);
          if (elect) STAMP(wg, 9);
        } else mbar_wait(BAR(B_KV1), 0);
        float oa[2][20];
        wg_fence();
#pragma unroll
        for (int m = 0; m < 4; m++) {
          const uint32_t* p = &pq[m & 1][8 * hh + 4 * (m >> 1)];
          wgmma_rs_n40<1>(oa[m & 1], p[0], p[1], p[2], p[3], dsc(s16 + (OFF_KVB >> 4) + hh * 160 + (m >> 1) * 16 + (8 << 16), 32), m >> 1);
        }
        wg_commit();
        wg_wait<0>();
#pragma unroll
        for (int mt = 0; mt < 2; mt++) {
          float (&o)[20] = oa[mt];
          keep(o);
          const uint32_t den = hadd(pk2(o[16], o[18]), 0x35863586u);
#pragma unroll
          for (int r = 0; r < 2; r++) {
            const float ri = rcp_fast(__uint_as_float(r ? (den & 0xFFFF0000u) : (den << 16)));
            uint4 u;
            u.x = pk2(o[2 * r] * ri, o[2 * r + 1] * ri);
            u.y = pk2(o[4 + 2 * r] * ri, o[5 + 2 * r] * ri);
            u.z = pk2(o[8 + 2 * r] * ri, o[9 + 2 * r] * ri);
            u.w = pk2(o[12 + 2 * r] * ri, o[13 + 2 * r] * ri);
            if (hh == 0) st_cg4(ot + (64 * mt + 8 * r) * 8, u); else ov[2 * mt + r] = u;
          }
        }
        if (hh == 0) {
          __syncwarp();
          if (lane == 0) mbar_arrive(BAR(B_ODONE));
          if (elect) STAMP(wg, 10);
        }
      };
      auto trickle = [&](const int qs) {
        const int m = qs - 2 * (OCH + O1D) - (TRICK - 1);
        if (m >= 0 && m < 4) {
          st_cg4(ot + 8 * 1024 + (64 * (m >> 1) + 8 * (m & 1)) * 8, ov[m]);
          if (m == 3) { __syncwarp(); if (lane == 0) mbar_arrive(BAR(B_ODONE1)); }
        }
      };
#pragma unroll
      for (int i = 0; i < 4; i++) {
        const bool nx = i < 3;
        const int n = nx ? i + 1 : i;
        const uint32_t vo = (i & 1) ? OFF_H + (i >> 1) * 16384 : OFF_VP;
        if (2 * i == OCH) ocalc(0);
        if (2 * i == OCH + O1D) ocalc(1);
        if (nx) {
          conv_m1(K, ux, xl + n * (XT_STRIDE >> 4));
          conv_m1(K, uh, hl + (n >> 1) * 1024 + (n & 1) * 256);
        }
        if (2 * i != OCH && 2 * i != OCH + O1D) { if (nx) { if (i > 0) wg_wait<3>(); else wg_wait<2>(); } else wg_wait<1>(); }
        keepu(X[i][0]); keepu(X[i][1]); keepu(H[i][0]); keepu(H[i][1]);
        conv_win(K, X[i], W);
        trickle(4 * i);
        conv_pw<0>(W, H[i], V0, dil);
        conv_pw<1>(W, H[i], V1, dil);
        trickle(4 * i + 1);
        wg_wait<2>();
        if (i > 0) { keepu(y); YOUT(i - 1); }
        if (2 * i + 1 == OCH) ocalc(0);
        if (2 * i + 1 == OCH + O1D) ocalc(1);
        if (nx) {
          keepu(ux); keepu(uh);
          if (lane == 0) mbar_arrive_cl(BAR(B_XFREE + 4 * wg + n), rank ^ 1);
          conv_s2(K, ux, X[n], dfl);
          wg_wait<1>();
        } else wg_wait<0>();
        keepu(V0); keepu(V1);
        trickle(4 * i + 2);
        if (i == 0) mbar_wait(BAR(B_H2), 0);
        conv_it<0>(K, V0, vst + vo);
        conv_it<1>(K, V1, vst + vo);
        bar_sync(1 + wg);
#pragma unroll
        for (int s = 0; s < 4; s++) ldsm4t(a[s], vld + vo + s * 512);
        if (nx) conv_s2(K, uh, H[n], dfl);
        conv_m4(y, a, d4l);
        trickle(4 * i + 3);
        if (i > 0 && lane < 2) mbar_arrive_cl(BAR(B_AFREE + i - 1), lane);
        if (elect && i < 3) STAMP(wg, i < 2 ? 6 + i : 9 + i);
      }
      wg_wait<0>(); keepu(y);
      YOUT(3);
      __syncwarp();
      if (lane == 0) mbar_arrive(BAR(B_Y));
      if (elect) STAMP(wg, 12);
    }
    {
      float acc[64];
#define G2_MMA(da, db, first) do { wg_fence(); _Pragma("unroll") for (int ks = 0; ks < 4; ks++) \
        wgmma_ss_n128<0, 1>(acc, dsc((da) + ks * 2, SW128), dsc((db) + ks * 128, SW128), ks || !(first)); wg_commit(); } while (0)
      const uint32_t a0 = s16 + wg * 512 + (1 << 16), b0 = s16 + (512 << 16);
      uint64_t ta = SLOT_A, tb = SLOT_B;
      uint32_t da = a0 + (SLOT_A & 15) * 1024, db = b0 + (SLOT_B & 15) * 1024, fb = BAR(B_FULL2);
      uint32_t cons = mapa(BAR(B_CONS2 - 1), t & 1);
      const bool rel = __shfl_sync(~0u, t, lane) < 2;
#pragma unroll 1
      for (int kb = 0; kb < HOLD2; kb++) {
        mbar_wait(fb, 0);
        if (kb == 0 && elect) { STAMP(wg, 13); GSTAMP(wg, 28); }
        G2_MMA(da, db, kb == 0);
        ta >>= 4; tb >>= 4;
        da = a0 + ((uint32_t)ta & 15) * 1024; db = b0 + ((uint32_t)tb & 15) * 1024; fb += 8;
        asm volatile("" : "+r"(da), "+r"(db));
        wg_wait<1>();
        if (kb > 0 && kb < 12 && rel) asm volatile("mbarrier.arrive.shared::cluster.b64 _, [%0];" ::"r"(cons) : "memory");
        cons += 8;
      }
#pragma unroll
      for (int kb = HOLD2; kb < 16; kb++) {
        if (wg == 1) mbar_wait(BAR(B_FULL2 + kb), 0);
        else if (kb == HOLD2) asm volatile("bar.sync 3, 256;" ::: "memory");
        G2_MMA(a0 + ((SLOT_A >> (4 * kb)) & 15) * 1024, b0 + ((SLOT_B >> (4 * kb)) & 15) * 1024, false);
      }
      if (wg == 1) asm volatile("bar.arrive 3, 256;" ::: "memory");
      const uint32_t stg = sb + wg * 8192 + w * 2048, so0 = ((SLOT_A >> 56) & 15) * 16384, so1 = ((SLOT_A >> 60) & 15) * 16384;
      const uint32_t lrow = stg + (8 * ((lane >> 3) & 1) + (lane & 7)) * 128 + (((lane >> 4) ^ (lane & 7)) << 4);
      const int col = 1024 + 256 * cb + 128 * rank, row = 128 * rb + 64 * wg + 16 * w;
      wg_wait<0>();
      keep(acc);
      if (elect) { STAMP(wg, 14); GSTAMP(wg, 29); }
#pragma unroll
      for (int cp = 0; cp < 8; cp++) {
        const float* a = &acc[8 * cp];
        stsm4((lrow ^ ((cp & 3) * 32)) + (cp >> 2 ? so1 : so0), pk2(a[0], a[1]), pk2(a[2], a[3]), pk2(a[4], a[5]), pk2(a[6], a[7]));
        if ((cp & 3) == 3) {
          fence_async();
          __syncwarp();
          if (elect_one()) tma2d_st(&P.tmOB, stg + (cp >> 2 ? so1 : so0), col + (cp >> 2) * 64, row);
        }
      }
      asm volatile("cp.async.bulk.commit_group;\ncp.async.bulk.wait_group.read 0;" ::: "memory");
      if (elect) {
        STAMP(wg, 15); GSTAMP(wg, 31); PDUMP(wg); if (wg == 0) PDUMP(2);
      }
    }
  } else {
    asm volatile("setmaxnreg.dec.sync.aligned.u32 56;");
    const int hw = warp - 9, g = lane >> 2, q = lane & 3;
#define sbar (bars + 8 * (B_STG - 18) + 16 * warp)
    if (warp == 8) {
      if (D1) __nanosleep(D1);
      int st = 1, pp = 1;
      const uint8_t* pfx = (const uint8_t*)P.x + (mb * 256 + hp * 16 + (lane & 15)) * 2048;
      const uint8_t* pfw = (const uint8_t*)P.w + (mb * 8 + (lane & 7)) * 6144 + (lane >> 3) * 2048 + hp * 128;
#pragma unroll 1
      for (int kb = 1; kb < 16; kb++) {
        if (kb >= 3) mbar_wait(BAR(B_EMPTY1 + st), pp);
        const uint32_t sa = sb + st * STAGE_BYTES;
        if (elect_one()) {
          mbar_expect(BAR(B_FULL1 + st), STAGE_BYTES);
          tma2d_mc(sa + rank * 16384, &P.tmX, kb * 64, mb * 256 + rank * 128, BAR(B_FULL1 + st));
          tma3d(sa + 32768, &P.tmW, hp * 64, kb * 64, 0, BAR(B_FULL1 + st));
        }
        if (kb == 1 && lane == 0) STAMP(2, 24);
        if (PFD && kb >= 2) {
#pragma unroll 1
          for (int j = kb == 2 ? 3 : kb + PFD; j <= kb + PFD && j < 16; j++) {
            if (lane < 16) asm volatile("prefetch.global.L2 [%0];" ::"l"(pfx + j * 128));
            if (lane < 24) asm volatile("prefetch.global.L2 [%0];" ::"l"(pfw + j * (64 * 6144)));
          }
          if (kb >= QPF && kb < QPF + 8) asm volatile("prefetch.global.L2 [%0];" ::"l"((const uint8_t*)P.q + (blockIdx.x * 256 + (kb - QPF) * 32 + lane) * 128));
          if (kb >= 4)
            asm volatile("prefetch.global.L2 [%0];" ::"l"(kb < 12 ? (const uint8_t*)P.h + ((2 * cl + rank) * 256 + (kb - 4) * 32 + lane) * 128
                                                                  : (const uint8_t*)P.wo + (blockIdx.x * 128 + (kb - 12) * 32 + lane) * 128));
        }
        if (++st == 3) { st = 0; pp ^= 1; }
      }
      if (lane == 0) STAMP(2, 1);
    } else {
      {
        const uint32_t clk0 = __shfl_sync(~0u, (uint32_t)clock(), 0), stg = sb + OFF_STG + hw * STG_STRIDE;
        const unsigned epoch = __shfl_sync(~0u, EPOCH, 0);
        const uint32_t tag = ~epoch & 1;
        uint32_t tap[2][4];
#pragma unroll
        for (int cg = 0; cg < 2; cg++) {
          const uint2 u = __ldg((const uint2*)(P.shift_k + (16 * cl + 8 * cg + g) * 4));
          tap[cg][0] = __byte_perm(u.x, 0, 0x1010); tap[cg][1] = __byte_perm(u.x, 0, 0x3232);
          tap[cg][2] = __byte_perm(u.y, 0, 0x1010); tap[cg][3] = __byte_perm(u.y, 0, 0x3232);
        }
        if (hw == 0 && lane < 8) *(float*)(smem + OFF_D + 4 * lane) = __bfloat162float(P.D[16 * cl + 8 * rank + lane]);
        if (hw == 1 && lane < 24) asm volatile("prefetch.global.L2 [%0];" ::"l"(P.thr + (lane + 24 * rank) * 32));
        if (hw == 0 && elect_one()) {
          *(volatile unsigned*)(smem + OFF_EPOCH) = epoch;
          mbar_expect(BAR(B_XRAW), 16384);
          mbar_expect(BAR(B_Y), 16384 + 64);
        }
        for (int i = hw * 32 + lane; i < 528; i += 96) st_tag4(P.part + (hp * 8 + mb) * 2176 + 4 * i, 0.f, 0.f, 0.f, 0.f, tag ^ 1);
        if (hw < 2 || lane < 2) st_tag4(P.kv + hp * 2176 + (4 * (hw < 2 ? 64 * mb + 32 * hw + lane : 512 + 8 * (mb & 1) + (mb & 6) + lane)), 0.f, 0.f, 0.f, 0.f, tag ^ 1);
        if (lane == 0) STAMP(3, hw);
        const uint32_t xo = sb + OFF_XT + g * XT_STRIDE + rank * 2048 + q * 4;
        const int krow = 8 + (lane & 7) - (lane >> 3);
        const uint32_t ka = stg + krow * 32 + ((krow & 4) << 2), va = stg + 2304 + lane * 32 + ((lane & 4) << 2);
        int ph = 0, b = 0;
#pragma unroll 1
        for (int ci = hw - 3; ci < 16; ci += 3) {
          const uint32_t bo = b ? OFF_F2F - OFF_STG : 0, bn = b ? 0 : OFF_F2F - OFF_STG;
          if (ci + 3 < 16) {
            while (__any_sync(~0u, (uint32_t)clock() - clk0 < HSTART + (ci + 3) * PACE)) __nanosleep(64);
            if (elect_one()) {
              mbar_expect(sbar + 8 * (b ^ 1), 2304 + 2048);
              tma2d(stg + bn, &P.tmK, 16 * cl, 1024 * rank + 64 * (ci + 3) - 8, sbar + 8 * (b ^ 1));
              tma2d(stg + bn + 2304, &P.tmV, 16 * cl, 1024 * rank + 64 * (ci + 3), sbar + 8 * (b ^ 1));
            }
          }
          if (ci >= 0) {
            mbar_wait(sbar + 8 * b, (ph >> b) & 1);
            ph ^= 1 << b;
#pragma unroll 1
            for (int grp = 0; grp < 2; grp++) {
#pragma unroll
              for (int cg = 0; cg < 2; cg++) {
                const uint32_t dst = mapa(xo + (ci >> 3) * 1024 + ((ci & 7) * 4 + 2 * grp) * 16, cg), xbar = mapa(BAR(B_XRAW), cg);
                uint32_t vv[4], kk[4][4];
                ldsm4t(vv, (va ^ (cg * 16)) + bo + grp * 1024);
#pragma unroll
                for (int rg = 0; rg < 4; rg++) ldsm4t(kk[rg], (ka ^ (cg * 16)) + bo + grp * 1024 + rg * 256);
#pragma unroll
                for (int rg = 0; rg < 4; rg++)
                  vv[rg] = hmul(hadd(hadd(hadd(hmul(kk[rg][3], tap[cg][3]), hmul(kk[rg][2], tap[cg][2])), hmul(kk[rg][1], tap[cg][1])), hmul(kk[rg][0], tap[cg][0])), vv[rg]);
                if (cg == rank) {
#pragma unroll
                  for (int rg = 0; rg < 4; rg++) asm volatile("st.shared.b32 [%0], %1;" ::"r"(dst + (rg & 1) * 512 + (rg >> 1) * 16), "r"(vv[rg]) : "memory");
                } else {
#pragma unroll
                  for (int rg = 0; rg < 4; rg++) st_async(dst + (rg & 1) * 512 + (rg >> 1) * 16, vv[rg], xbar);
                }
              }
            }
          }
          b ^= 1;
        }
      }
      if (lane == 0 && hw == 0) STAMP(3, 3);
      asm volatile("bar.sync 4, 96;" ::: "memory");
      if (hw == 0 && elect_one()) { mbar_expect(BAR(B_XT), 10240); bulk_ld(sb + OFF_F2F, P.img, 10240, BAR(B_XT)); }
      mbar_wait(BAR(B_XRAW), 0);
    }
    int e1 = 0;
#pragma unroll 1
    for (int n = hw < 0 ? 3 : 0; n < 4; n++) {
      const bool isH = n >= 3;
      const int c = isH ? (warp & 1) + 2 * (warp & 2) : hw + 3 * n;
      if (c < 8) {
        int ln;
        asm volatile("mov.u32 %0, %%laneid;" : "=r"(ln));
        uint8_t* dst = smem + (isH ? OFF_H + (c & 2) * 8192 + (c >> 2) * 8192 + (c & 1) * 4096 : OFF_XT + c * XT_STRIDE) + ((ln >> 4) * 512 + (ln & 15) * 16);
        const uint8_t* src0 = isH ? (const uint8_t*)P.h + (16 * cl + 8 * rank + c) * 4096 + ((ln & 15) * 32 + (ln & 16)) : dst;
        const uint8_t* src1 = src0 + (isH ? 512 : 256);
        uint32_t v[32];
#pragma unroll
        for (int i = 0; i < 8; i++) {
          const uint4 u = *(const uint4*)(((i & 1) ? src1 : src0) + (i >> 1) * 1024);
          v[4 * i] = u.x; v[4 * i + 1] = u.y; v[4 * i + 2] = u.z; v[4 * i + 3] = u.w;
        }
        if (isH) mbar_wait(BAR(B_XT), 0);
        const float f0 = __uint_as_float(v[0] << 16) + ((isH && ln == 0) ? *(const float*)(smem + OFF_D + 4 * c) : 0.f);
        const int e = norm_exp(v, f0);
        norm_cvt(v, f0, e);
        if (isH) mbar_wait(BAR(B_SFREE), 0);
        else if (ln == 0) smem[OFF_EX + c] = e;
        e1 = e;
#pragma unroll
        for (int i = 0; i < 8; i++)
          *(uint4*)(dst + (i >> 1) * 1024 + (i & 1) * 256) = make_uint4(v[4 * i], v[4 * i + 1], v[4 * i + 2], v[4 * i + 3]);
        if (n < 2 && elect_one()) {
          if (n == 0) mbar_expect(sbar, 4096);
          tma3d(sb + OFF_STG + 2048 * c, &P.tmQ, 16 * cl, 64 * rank, 2 * c, sbar);
        }
      }
      if (n >= 2) {
        fence_async();
        __syncwarp();
        if (lane == 0) { mbar_arrive(BAR(isH ? B_H : B_XT)); STAMP(3, (isH ? 17 : 13) + hw); }
      }
    }
#define SLOT(tab, kb) (sb + ((uint32_t)((tab) >> (4 * (kb))) & 15) * 16384)
#define KT(kb) (!OLOC ? (kb) : (kb) == 0 ? hq : (kb) == hq ? 0 : (kb))
#define LOAD_B(kb) tma4d(SLOT(SLOT_B, kb), &P.tmWo, 0, ((kb) >> 3) * 32, 2 * (KT(kb) & 7), 4 * cb + 2 * rank, BAR(B_FULL2 + (kb)))
#define LOAD_A(kb) bulk_ld_mc(SLOT(SLOT_A, kb) + rank * 8192, P.o + rb * OBLK + KT(kb) * 1024 + rank * 512, 8192, BAR(B_FULL2 + (kb)))
    asm volatile("setmaxnreg.inc.sync.aligned.u32 104;");
    {
    int tid;
    asm volatile("mov.u32 %0, %%tid.x;" : "=r"(tid));
    const int lane = tid & 31, g = lane >> 2, q = lane & 3;
    const unsigned epoch = *(volatile unsigned*)(smem + OFF_EPOCH);
    const uint32_t tag = ~epoch & 1;
    const int pi = hw < 2 ? 64 * mb - 288 + tid : 512 + 8 * (mb & 1) + (mb & 6) + (lane & 1);
    const float* psrc = P.part + hp * 8 * 2176 + 4 * pi;
    uint4 f[8];
    {
      const uint32_t s16 = (sb & 0x3FFFF) >> 4;
      const int t = tid & 127, c = 2 + (warp & 1) + 2 * (warp & 2);
      const uint4* hp4 = (const uint4*)(P.h + (16 * cl + 8 * rank + c) * 2048) + ((lane & 15) * 2 + (lane >> 4));
      uint32_t v[32];
#pragma unroll
      for (int i = 0; i < 8; i++) { const uint4 u = ld_na4(hp4 + i * 32); v[4 * i] = u.x; v[4 * i + 1] = u.y; v[4 * i + 2] = u.z; v[4 * i + 3] = u.w; }
      float kva[36];
#pragma unroll
      for (int mt = 0; mt < 2; mt++) {
        mbar_wait(BAR(B_PKRDY + mt), 0);
        wg_fence();
#pragma unroll
        for (int ks = 0; ks < 8; ks++) {
          const uint32_t o = (ks >> 2) * 1024 + mt * 512 + (ks & 3) * 128, vb = (2 * STAGE_BYTES >> 4) + o;
          wgmma_ss_n72<1, 1>(kva, dsc(s16 + o + (1 << 16), SW128), dsc(s16 + vb + (((OFF_ONES >> 4) - vb) << 16), SW128), (mt | ks) != 0);
        }
        wg_commit();
        if (mt == 0 && hw < 0) {
          mbar_wait(BAR(B_G1DONE), 0);
          if (elect_one()) {
#pragma unroll
            for (int kb = 0; kb < BEARLY; kb++) { mbar_expect(BAR(B_FULL2 + kb), 16384); LOAD_B(kb); }
          }
        }
      }
      float* pdst = P.part + (hp * 8 + mb) * 2176 + t * 4;
      float* zdst = P.part + (hp * 8 + mb) * 2176 + 2048 + (t >> 1);
      asm volatile("" : "+l"(pdst), "+l"(zdst));
      wg_wait<0>();
      keep(kva);
      if (hw < 1) {
#pragma unroll
        for (int c = 0; c < 4; c++) st_tag4(pdst + c * 512, kva[4 * c], kva[4 * c + 1], kva[4 * c + 2], kva[4 * c + 3], tag);
      } else {
#pragma unroll
        for (int c = 4; c < 8; c++) st_tag4(pdst + (c - 4) * 512, kva[4 * c], kva[4 * c + 1], kva[4 * c + 2], kva[4 * c + 3], tag);
      }
      const float z2 = __shfl_down_sync(~0u, kva[32], 4), z3 = __shfl_down_sync(~0u, kva[34], 4);
      if (!(lane & 7)) st_tag4(zdst, kva[32], kva[34], z2, z3, tag);
      if (lane == 0) mbar_arrive(BAR(B_PKFREE));
      const uint32_t cst = clock();
      if (hw == 0 && lane == 0) STAMP(3, 24);
      const float f0 = __uint_as_float(v[0] << 16) + (lane == 0 ? *(const float*)(smem + OFF_D + 4 * c) : 0.f);
      const int e = norm_exp(v, f0);
      norm_cvt(v, f0, e);
      if (hw >= 0) {
        while (__any_sync(~0u, (uint32_t)clock() - cst < PD1)) __nanosleep(20);
        if (hw == 0 && lane == 0) STAMP(3, 20);
#pragma unroll
        for (int p = 0; p < 8; p++) f[p] = ld_rlx4(psrc + p * 2176);
      }
      uint8_t* dst = smem + OFF_H + 16384 + (warp & 3) * 4096 + (lane >> 4) * 512 + (lane & 15) * 16;
#pragma unroll
      for (int i = 0; i < 8; i++)
        *(uint4*)(dst + (i >> 1) * 1024 + (i & 1) * 256) = make_uint4(v[4 * i], v[4 * i + 1], v[4 * i + 2], v[4 * i + 3]);
      if (lane < 4) {
        const int cc = c - (lane & 2);
        st_async(mapa(sb + OFF_SCALE + (8 * rank + cc) * 4, lane & 1), min(max(((lane & 2) ? e1 : e) + smem[OFF_EX + cc] - 124, 1), 254) << 23, mapa(BAR(B_Y), lane & 1));
      }
    }
#define H2_READY() do { fence_async(); __syncwarp(); if (lane == 0) mbar_arrive(BAR(B_H2)); } while (0)
    if (warp == 8) {
      H2_READY();
      mbar_wait(BAR(B_PKFREE), 0);
      {
        const uint32_t c0 = clock();
#pragma unroll 1
        for (int i = 0; i < 2 * NPRE - 2 * BEARLY; i++) {
          const int kb = (i >> 1) + BEARLY;
          while (__any_sync(~0u, (uint32_t)clock() - c0 < i * BPACE)) __nanosleep(32);
          if (elect_one()) {
            if (!(i & 1)) mbar_expect(BAR(B_FULL2 + kb), 16384);
            tma4d(SLOT(SLOT_B, kb) + (i & 1) * 8192, &P.tmWo1, 0, 0, 2 * KT(kb), 4 * cb + 2 * rank + (i & 1), BAR(B_FULL2 + kb));
            if (i == 0) mbar_expect(BAR(B_Q), 8192);
            if (i < 4) tma3d(sb + OFF_SPARE + 2048 * i, &P.tmQ, 16 * cl, 64 * rank + 32 * (i >> 1), 2 * ((i + 6) & 7), BAR(B_Q));
          }
        }
      }
      if (lane == 0) STAMP(2, 2);
      if (OLOC) {
        if (elect_one()) mbar_expect(BAR(B_FULL2), 16384);
        mbar_wait(BAR(B_OLOC), 0);
        asm volatile("fence.acquire.cluster;\nfence.proxy.async.global;" ::: "memory");
        if (elect_one()) LOAD_A(0);
      }
      mbar_wait(BAR(B_AFREE), 0);
      if (elect_one()) mbar_expect(BAR(B_FULL2 + OLOC), 16384);
      {
        const uint32_t dst = SLOT(SLOT_A, OLOC) + rank * 8192;
        const uint4* src = P.o + rb * OBLK + KT(OLOC) * 1024 + rank * 512;
        poll_ge(OCNT(rb, 0), 16 * (epoch + 1));
        asm volatile("fence.proxy.async.global;" ::: "memory");
        if (lane == 0) STAMP(2, 3);
        if (elect_one()) bulk_ld_mc(dst, src, 8192, BAR(B_FULL2 + OLOC));
        if (lane == 0) STAMP(3, 23);
      }
#pragma unroll 1
      for (int kb = 1 + OLOC; kb < NPRE; kb++) {
        mbar_wait(BAR(kb < 4 ? B_AFREE + kb - 1 : B_CONS2), 0);
        if (elect_one()) { mbar_expect(BAR(B_FULL2 + kb), 16384); LOAD_A(kb); }
      }
#pragma unroll 1
      for (int kb = NPRE; kb < 16; kb++) {
        mbar_wait(BAR(B_CONS2 + kb - 5), 0);
        if (kb == 8) mbar_wait(BAR(B_O1RDY), 0);
        if (elect_one()) { mbar_expect(BAR(B_FULL2 + kb), 32768); LOAD_A(kb); LOAD_B(kb); }
      }
      if (lane == 0) { EPOCH = epoch + 1; STAMP(2, 5); }
    } else {
      {
#pragma unroll 1
        for (int n = 0; __any_sync(~0u, stale8(f, tag) & 1); n++) {
#pragma unroll
          for (int p = 0; p < 8; p++) ld_stale4(f[p], psrc + p * 2176, tag);
          if (n > SPIN_LIMIT) __trap();
        }
        float s0 = 0.f, s1 = 0.f, s2 = 0.f, s3 = 0.f;
#pragma unroll
        for (int p = 0; p < 8; p++) { s0 += __uint_as_float(f[p].x); s1 += __uint_as_float(f[p].y); s2 += __uint_as_float(f[p].z); s3 += __uint_as_float(f[p].w); }
        if (hw < 2 || lane < 2) st_tag4(P.kv + hp * 2176 + (4 * pi), s0, s1, s2, s3, tag);
      }
      const uint32_t cs2 = clock();
      if (lane == 0 && hw == 0) STAMP(3, 8);
      H2_READY();
      if (hw == 2) {
        unsigned* cnt = OCNT(2 * mb + lane, 0);
#pragma unroll 1
        for (int hh = 0; hh < 2; hh++) {
          mbar_wait(BAR(hh ? B_ODONE1 : B_ODONE), 0);
          if (lane < 2) asm volatile("red.release.gpu.global.add.u32 [%0], 1;" ::"l"(cnt) : "memory");
          if (OLOC && hh == 0 && lane < 2) mbar_arrive_cl(BAR(B_OLOC), lane);
          cnt += 32;
          if (lane == 0) STAMP(3, hh ? 6 : 7);
        }
        poll_ge(OCNT(rb, 1), 16 * (epoch + 1));
        asm volatile("fence.proxy.async.global;" ::: "memory");
        if (lane == 0) { mbar_arrive(BAR(B_O1RDY)); STAMP(2, 4); }
        __syncwarp();
      } else {
        const int t = tid - 288;
        const float* src = P.kv + hp * 2176 + 4 * (t + 32 * hw);
        const float* zsrc = P.kv + hp * 2176 + (2048 + (t & 48) + 2 * (lane & 6));
        mbar_wait(BAR(B_PKFREE), 0);
        while (__any_sync(~0u, (uint32_t)clock() - cs2 < PD2)) __nanosleep(20);
        uint4 zp = ld_rlx4(zsrc);
#pragma unroll
        for (int p = 0; p < 8; p++) f[p] = ld_rlx4(src + 4 * ((p & 3) * 128 + (p >> 2) * 32));
        if (!opaque_true()) __trap();
#pragma unroll 1
        for (int n = 0; __any_sync(~0u, (stale8(f, tag) | (zp.x ^ tag)) & 1); n++) {
          ld_stale4(zp, zsrc, tag);
#pragma unroll
          for (int p = 0; p < 8; p++) ld_stale4(f[p], src + 4 * ((p & 3) * 128 + (p >> 2) * 32), tag);
          if (n > SPIN_LIMIT) __trap();
        }
#define PK2U(a, b) pk2(__uint_as_float(a), __uint_as_float(b))
        const uint32_t zf = (lane & 1) ? ((lane & 8) ? zp.w : zp.z) : ((lane & 8) ? zp.y : zp.x);
        const uint32_t zz = PK2U(zf, zf);
        *(uint4*)(smem + OFF_KVB + hw * 2560 + 2048 + lane * 16) = make_uint4(zz, zz, zz, zz);
#pragma unroll
        for (int hh = 0; hh < 2; hh++) {
          const uint4* ff = &f[4 * hh];
          uint8_t* dst = smem + OFF_KVB + hw * 2560 + q * 512 + (16 * hh + g) * 16;
          *(uint4*)dst = make_uint4(PK2U(ff[0].x, ff[0].y), PK2U(ff[1].x, ff[1].y), PK2U(ff[2].x, ff[2].y), PK2U(ff[3].x, ff[3].y));
          *(uint4*)(dst + 128) = make_uint4(PK2U(ff[0].z, ff[0].w), PK2U(ff[1].z, ff[1].w), PK2U(ff[2].z, ff[2].w), PK2U(ff[3].z, ff[3].w));
        }
        fence_async();
        __syncwarp();
        if (lane == 0) { mbar_arrive(BAR(hw ? B_KV1 : B_KV)); if (hw == 0) STAMP(3, 9); }
      }
#define QBUF(ci) (sb + 2048 * (ci) + ((ci) < 6 ? OFF_STG : (ci) < 10 ? OFF_SPARE - 6 * 2048 : OFF_F2F - 10 * 2048))
      mbar_wait(BAR(B_Y), 0);
      if (elect_one()) {
        mbar_expect(sbar + 8, 4096);
#pragma unroll 1
        for (int ci = hw ? hw + 9 : 12; ci < 16; ci += 3) tma3d(QBUF(ci), &P.tmQ, 16 * cl, 64 * rank + 32, 2 * (ci & 7), sbar + 8);
      }
      mbar_wait(BAR(B_Q), 0);
      mbar_wait(sbar, hw == 0);
      {
        const float2 sc0 = *(const float2*)(smem + OFF_SCALE + 8 * q), sc1 = *(const float2*)(smem + OFF_SCALE + 32 + 8 * q);
        const uint32_t yl = sb + OFF_XT + (lane & 7) * XT_STRIDE + (lane >> 3) * 16;
#pragma unroll 1
        for (int ci = hw; ci < 16; ci += 3) {
          const uint32_t qb = QBUF(ci);
          if (ci >= 10) mbar_wait(sbar + 8, 1);
#pragma unroll 1
          for (int nl = 0; nl < 2; nl++) {
            uint32_t yy[2][4], qq[2][4];
            const uint32_t qa = qb + lane * 32 + ((lane & 4) << 2) + nl * 1024;
#pragma unroll
            for (int cg = 0; cg < 2; cg++) { ldsm4t(yy[cg], yl + cg * 2048 + (2 * ci + nl) * 64); ldsm4(qq[cg], qa ^ (cg * 16)); }
#pragma unroll
            for (int cg = 0; cg < 2; cg++) {
              const float2 sc = cg ? sc1 : sc0;
#pragma unroll
              for (int m = 0; m < 4; m++) {
                const float2 f = __half22float2(*(const __half2*)&yy[cg][m]);
                qq[cg][m] = hmul(qq[cg][m], pk2(f.x * sc.x, f.y * sc.y));
              }
              stsm4(qa ^ (cg * 16), qq[cg][0], qq[cg][1], qq[cg][2], qq[cg][3]);
            }
          }
          fence_async();
          __syncwarp();
          if (elect_one()) tma3d_st(&P.tmOA, qb, 16 * cl, 64 * rank + 32 * (ci >> 3), 2 * (ci & 7));
        }
        asm volatile("cp.async.bulk.commit_group;\ncp.async.bulk.wait_group.read 0;" ::: "memory");
      }
      if (lane == 0) STAMP(3, 10 + hw);
    }
    }
  }
}

typedef CUresult (*EncodeFn)(CUtensorMap*, CUtensorMapDataType, cuuint32_t, void*, const cuuint64_t*, const cuuint64_t*,
                             const cuuint32_t*, const cuuint32_t*, CUtensorMapInterleave, CUtensorMapSwizzle,
                             CUtensorMapL2promotion, CUtensorMapFloatOOBfill);

static void enc(EncodeFn fn, CUtensorMap* m, const void* p, int rank, const cuuint64_t* dims, const cuuint64_t* strides,
                const cuuint32_t* box, CUtensorMapSwizzle swz, CUtensorMapL2promotion promo) {
  cuuint32_t es[4] = {1, 1, 1, 1};
  fn(m, CU_TENSOR_MAP_DATA_TYPE_BFLOAT16, rank, (void*)p, dims, strides, box, es, CU_TENSOR_MAP_INTERLEAVE_NONE, swz, promo,
     CU_TENSOR_MAP_FLOAT_OOB_FILL_NONE);
}

extern "C" void kernel_launch(void* const* d_in, const int* in_sizes, int n_in, void* d_out, int out_size) {
  void* fp = nullptr;
  cudaDriverEntryPointQueryResult qr;
  cudaGetDriverEntryPoint("cuTensorMapEncodeTiled", &fp, cudaEnableDefault, &qr);
  EncodeFn fn = (EncodeFn)fp;
  Params P;
  P.shift_k = (const __nv_bfloat16*)d_in[3]; P.h = (const __nv_bfloat16*)d_in[4]; P.D = (const __nv_bfloat16*)d_in[5];
  P.q = (const __nv_bfloat16*)d_in[0];
  cudaGetSymbolAddress((void**)&P.part, g_part); cudaGetSymbolAddress((void**)&P.kv, g_kv); cudaGetSymbolAddress((void**)&P.o, g_o);
  cudaGetSymbolAddress((void**)&P.thr, c_thr); cudaGetSymbolAddress((void**)&P.img, c_img);
  P.x = (const __nv_bfloat16*)d_in[6]; P.w = (const __nv_bfloat16*)d_in[7]; P.wo = (const __nv_bfloat16*)d_in[8];
  const CUtensorMapSwizzle S128 = CU_TENSOR_MAP_SWIZZLE_128B, S32 = CU_TENSOR_MAP_SWIZZLE_32B;
  const CUtensorMapL2promotion P0 = CU_TENSOR_MAP_L2_PROMOTION_NONE, P128 = CU_TENSOR_MAP_L2_PROMOTION_L2_128B;
  { cuuint64_t d[2] = {1024, 2048}, s[1] = {2048}; cuuint32_t b[2] = {64, 128}; enc(fn, &P.tmX, d_in[6], 2, d, s, b, S128, P128); }
  { cuuint64_t d[2] = {1024, 2048}, s[1] = {2048}; cuuint32_t b[2] = {64, 64}; enc(fn, &P.tmX0, d_in[6], 2, d, s, b, S128, P128); }
  { cuuint64_t d[3] = {1024, 1024, 3}, s[2] = {6144, 2048}; cuuint32_t b[3] = {64, 64, 3}; enc(fn, &P.tmW, d_in[7], 3, d, s, b, S128, P128); }
  { cuuint64_t d[4] = {64, 64, 16, 16}, s[3] = {2048, 131072, 128}; cuuint32_t b[4] = {64, 32, 2, 2}; enc(fn, &P.tmWo, d_in[8], 4, d, s, b, S128, P128); }
  { cuuint64_t d[4] = {64, 64, 16, 16}, s[3] = {2048, 131072, 128}; cuuint32_t b[4] = {64, 32, 2, 1}; enc(fn, &P.tmWo1, d_in[8], 4, d, s, b, S128, P128); }
  { cuuint64_t d[2] = {1024, 2048}, s[1] = {2048}; cuuint32_t b[2] = {16, 72}; enc(fn, &P.tmK, d_in[1], 2, d, s, b, S32, P128); }
  { cuuint64_t d[2] = {1024, 2048}, s[1] = {2048}; cuuint32_t b[2] = {16, 64}; enc(fn, &P.tmV, d_in[2], 2, d, s, b, S32, P128); }
  { cuuint64_t d[3] = {1024, 128, 16}, s[2] = {32768, 2048}; cuuint32_t b[3] = {16, 32, 2}; enc(fn, &P.tmQ, d_in[0], 3, d, s, b, S32, P128); }
  { cuuint64_t d[3] = {1024, 128, 16}, s[2] = {65536, 4096}; cuuint32_t b[3] = {16, 32, 2}; enc(fn, &P.tmOA, d_out, 3, d, s, b, S32, P0); }
  { cuuint64_t d[2] = {2048, 2048}, s[1] = {4096}; cuuint32_t b[2] = {64, 16}; enc(fn, &P.tmOB, d_out, 2, d, s, b, S128, P0); }
  cudaFuncSetAttribute(fused_kernel, cudaFuncAttributeMaxDynamicSharedMemorySize, SMEM_TOTAL);
  fused_kernel<<<128, 384, SMEM_TOTAL>>>(P);
}
```

```cpp
#include <cuda_runtime.h>
#include <cuda_bf16.h>
#include <cuda_fp16.h>
#include <cuda.h>
#include <stdint.h>

template<int TA, int TB, int SA=1> __device__ __forceinline__ void wgmma_ss_n192(float (&d)[96], uint64_t da, uint64_t db, int scale_d) {
  asm volatile("{\n.reg .pred p;\nsetp.ne.b32 p, %98, 0;\n"
    "wgmma.mma_async.sync.aligned.m64n192k16.f32.bf16.bf16 {%0, %1, %2, %3, %4, %5, %6, %7, %8, %9, %10, %11, %12, %13, %14, %15, %16, %17, %18, %19, %20, %21, %22, %23, %24, %25, %26, %27, %28, %29, %30, %31, %32, %33, %34, %35, %36, %37, %38, %39, %40, %41, %42, %43, %44, %45, %46, %47, %48, %49, %50, %51, %52, %53, %54, %55, %56, %57, %58, %59, %60, %61, %62, %63, %64, %65, %66, %67, %68, %69, %70, %71, %72, %73, %74, %75, %76, %77, %78, %79, %80, %81, %82, %83, %84, %85, %86, %87, %88, %89, %90, %91, %92, %93, %94, %95}, %96, %97, p, %101, 1, %99, %100;\n}\n"
    : "+f"(d[0]), "+f"(d[1]), "+f"(d[2]), "+f"(d[3]), "+f"(d[4]), "+f"(d[5]), "+f"(d[6]), "+f"(d[7]), "+f"(d[8]), "+f"(d[9]), "+f"(d[10]), "+f"(d[11]), "+f"(d[12]), "+f"(d[13]), "+f"(d[14]), "+f"(d[15]), "+f"(d[16]), "+f"(d[17]), "+f"(d[18]), "+f"(d[19]), "+f"(d[20]), "+f"(d[21]), "+f"(d[22]), "+f"(d[23]), "+f"(d[24]), "+f"(d[25]), "+f"(d[26]), "+f"(d[27]), "+f"(d[28]), "+f"(d[29]), "+f"(d[30]), "+f"(d[31]), "+f"(d[32]), "+f"(d[33]), "+f"(d[34]), "+f"(d[35]), "+f"(d[36]), "+f"(d[37]), "+f"(d[38]), "+f"(d[39]), "+f"(d[40]), "+f"(d[41]), "+f"(d[42]), "+f"(d[43]), "+f"(d[44]), "+f"(d[45]), "+f"(d[46]), "+f"(d[47]), "+f"(d[48]), "+f"(d[49]), "+f"(d[50]), "+f"(d[51]), "+f"(d[52]), "+f"(d[53]), "+f"(d[54]), "+f"(d[55]), "+f"(d[56]), "+f"(d[57]), "+f"(d[58]), "+f"(d[59]), "+f"(d[60]), "+f"(d[61]), "+f"(d[62]), "+f"(d[63]), "+f"(d[64]), "+f"(d[65]), "+f"(d[66]), "+f"(d[67]), "+f"(d[68]), "+f"(d[69]), "+f"(d[70]), "+f"(d[71]), "+f"(d[72]), "+f"(d[73]), "+f"(d[74]), "+f"(d[75]), "+f"(d[76]), "+f"(d[77]), "+f"(d[78]), "+f"(d[79]), "+f"(d[80]), "+f"(d[81]), "+f"(d[82]), "+f"(d[83]), "+f"(d[84]), "+f"(d[85]), "+f"(d[86]), "+f"(d[87]), "+f"(d[88]), "+f"(d[89]), "+f"(d[90]), "+f"(d[91]), "+f"(d[92]), "+f"(d[93]), "+f"(d[94]), "+f"(d[95])
    : "l"(da), "l"(db), "r"(scale_d), "n"(TA), "n"(TB), "n"(SA));
}
template<int TA, int TB, int SA=1> __device__ __forceinline__ void wgmma_ss_n128(float (&d)[64], uint64_t da, uint64_t db, int scale_d) {
  asm volatile("{\n.reg .pred p;\nsetp.ne.b32 p, %66, 0;\n"
    "wgmma.mma_async.sync.aligned.m64n128k16.f32.bf16.bf16 {%0, %1, %2, %3, %4, %5, %6, %7, %8, %9, %10, %11, %12, %13, %14, %15, %16, %17, %18, %19, %20, %21, %22, %23, %24, %25, %26, %27, %28, %29, %30, %31, %32, %33, %34, %35, %36, %37, %38, %39, %40, %41, %42, %43, %44, %45, %46, %47, %48, %49, %50, %51, %52, %53, %54, %55, %56, %57, %58, %59, %60, %61, %62, %63}, %64, %65, p, %69, 1, %67, %68;\n}\n"
    : "+f"(d[0]), "+f"(d[1]), "+f"(d[2]), "+f"(d[3]), "+f"(d[4]), "+f"(d[5]), "+f"(d[6]), "+f"(d[7]), "+f"(d[8]), "+f"(d[9]), "+f"(d[10]), "+f"(d[11]), "+f"(d[12]), "+f"(d[13]), "+f"(d[14]), "+f"(d[15]), "+f"(d[16]), "+f"(d[17]), "+f"(d[18]), "+f"(d[19]), "+f"(d[20]), "+f"(d[21]), "+f"(d[22]), "+f"(d[23]), "+f"(d[24]), "+f"(d[25]), "+f"(d[26]), "+f"(d[27]), "+f"(d[28]), "+f"(d[29]), "+f"(d[30]), "+f"(d[31]), "+f"(d[32]), "+f"(d[33]), "+f"(d[34]), "+f"(d[35]), "+f"(d[36]), "+f"(d[37]), "+f"(d[38]), "+f"(d[39]), "+f"(d[40]), "+f"(d[41]), "+f"(d[42]), "+f"(d[43]), "+f"(d[44]), "+f"(d[45]), "+f"(d[46]), "+f"(d[47]), "+f"(d[48]), "+f"(d[49]), "+f"(d[50]), "+f"(d[51]), "+f"(d[52]), "+f"(d[53]), "+f"(d[54]), "+f"(d[55]), "+f"(d[56]), "+f"(d[57]), "+f"(d[58]), "+f"(d[59]), "+f"(d[60]), "+f"(d[61]), "+f"(d[62]), "+f"(d[63])
    : "l"(da), "l"(db), "r"(scale_d), "n"(TA), "n"(TB), "n"(SA));
}
template<int TA, int TB, int SA=1> __device__ __forceinline__ void wgmma_ss_n72(float (&d)[36], uint64_t da, uint64_t db, int scale_d) {
  asm volatile("{\n.reg .pred p;\nsetp.ne.b32 p, %38, 0;\n"
    "wgmma.mma_async.sync.aligned.m64n72k16.f32.bf16.bf16 {%0, %1, %2, %3, %4, %5, %6, %7, %8, %9, %10, %11, %12, %13, %14, %15, %16, %17, %18, %19, %20, %21, %22, %23, %24, %25, %26, %27, %28, %29, %30, %31, %32, %33, %34, %35}, %36, %37, p, %41, 1, %39, %40;\n}\n"
    : "+f"(d[0]), "+f"(d[1]), "+f"(d[2]), "+f"(d[3]), "+f"(d[4]), "+f"(d[5]), "+f"(d[6]), "+f"(d[7]), "+f"(d[8]), "+f"(d[9]), "+f"(d[10]), "+f"(d[11]), "+f"(d[12]), "+f"(d[13]), "+f"(d[14]), "+f"(d[15]), "+f"(d[16]), "+f"(d[17]), "+f"(d[18]), "+f"(d[19]), "+f"(d[20]), "+f"(d[21]), "+f"(d[22]), "+f"(d[23]), "+f"(d[24]), "+f"(d[25]), "+f"(d[26]), "+f"(d[27]), "+f"(d[28]), "+f"(d[29]), "+f"(d[30]), "+f"(d[31]), "+f"(d[32]), "+f"(d[33]), "+f"(d[34]), "+f"(d[35])
    : "l"(da), "l"(db), "r"(scale_d), "n"(TA), "n"(TB), "n"(SA));
}
template<int TB, int SA=1> __device__ __forceinline__ void wgmma_rs_n40(float (&d)[20], uint32_t a0, uint32_t a1, uint32_t a2, uint32_t a3, uint64_t db, int scale_d) {
  asm volatile("{\n.reg .pred p;\nsetp.ne.b32 p, %25, 0;\n"
    "wgmma.mma_async.sync.aligned.m64n40k16.f32.bf16.bf16 {%0, %1, %2, %3, %4, %5, %6, %7, %8, %9, %10, %11, %12, %13, %14, %15, %16, %17, %18, %19}, {%20, %21, %22, %23}, %24, p, %27, 1, %26;\n}\n"
    : "+f"(d[0]), "+f"(d[1]), "+f"(d[2]), "+f"(d[3]), "+f"(d[4]), "+f"(d[5]), "+f"(d[6]), "+f"(d[7]), "+f"(d[8]), "+f"(d[9]), "+f"(d[10]), "+f"(d[11]), "+f"(d[12]), "+f"(d[13]), "+f"(d[14]), "+f"(d[15]), "+f"(d[16]), "+f"(d[17]), "+f"(d[18]), "+f"(d[19])
    : "r"(a0), "r"(a1), "r"(a2), "r"(a3), "l"(db), "r"(scale_d), "n"(TB), "n"(SA));
}
template<int TB> __device__ __forceinline__ void wgmma_hrs_n64(uint32_t (&d)[16], uint32_t a0, uint32_t a1, uint32_t a2, uint32_t a3, uint64_t db, int scale_d) {
  asm volatile("{\n.reg .pred p;\nsetp.ne.b32 p, %21, 0;\n"
    "wgmma.mma_async.sync.aligned.m64n64k16.f16.f16.f16 {%0, %1, %2, %3, %4, %5, %6, %7, %8, %9, %10, %11, %12, %13, %14, %15}, {%16, %17, %18, %19}, %20, p, 1, 1, %22;\n}\n"
    : "+r"(d[0]), "+r"(d[1]), "+r"(d[2]), "+r"(d[3]), "+r"(d[4]), "+r"(d[5]), "+r"(d[6]), "+r"(d[7]), "+r"(d[8]), "+r"(d[9]), "+r"(d[10]), "+r"(d[11]), "+r"(d[12]), "+r"(d[13]), "+r"(d[14]), "+r"(d[15])
    : "r"(a0), "r"(a1), "r"(a2), "r"(a3), "l"(db), "r"(scale_d), "n"(TB));
}
template<int TB> __device__ __forceinline__ void wgmma_hrs_n32(uint32_t (&d)[8], uint32_t a0, uint32_t a1, uint32_t a2, uint32_t a3, uint64_t db, int scale_d) {
  asm volatile("{\n.reg .pred p;\nsetp.ne.b32 p, %13, 0;\n"
    "wgmma.mma_async.sync.aligned.m64n32k16.f16.f16.f16 {%0, %1, %2, %3, %4, %5, %6, %7}, {%8, %9, %10, %11}, %12, p, 1, 1, %14;\n}\n"
    : "+r"(d[0]), "+r"(d[1]), "+r"(d[2]), "+r"(d[3]), "+r"(d[4]), "+r"(d[5]), "+r"(d[6]), "+r"(d[7])
    : "r"(a0), "r"(a1), "r"(a2), "r"(a3), "l"(db), "r"(scale_d), "n"(TB));
}

__device__ __align__(128) const uint32_t c_thr[1536] = {
  0x33fb33ff,0xa49c9de4,0x33273352,0xaf2cae76,0x33e233f1,0xa96ca7bd,0x32c432f7,0xb045afdd,0x33b733cf,0xac3eaaf7,0x3250328c,0xb0eab099,
  0x3378339a,0xadbcacff,0x31cd3211,0xb182b137,0x33d033fb,0xaadea46a,0x299e2d17,0xb3e0b396,0x32fb337a,0xafd2adb1,0xa78b1f76,0xb3f2b3ff,
  0x318b3254,0xb1c5b0e5,0xae6bac32,0xb354b3b8,0x2f4230a3,0xb321b285,0xb133b040,0xb215b2c7,0x337c33f2,0xada5a759,0xb179afc8,0xb1d6b2fe,
  0x31463293,0xb204b08e,0xb394b2ba,0xad23b055,0x2b402f4e,0xb3cbb31e,0xb3e4b3f9,0x293ba533,0xac269c52,0xb3bab400,0xb258b357,0x30e02e5f,
  0x330133e5,0xafbda922,0xb3f3b3c9,0x2727ab59,0x2deb314a,0xb36fb200,0xb194b32f,0x31bc2f0a,0xacdb2084,0xb39fb3ff,0xa565aea4,0x33f93347,
  0xb2b6b0db,0xb05ab25c,0x30892c1a,0x329733bc,0x326033d4,0xb0d6aa94,0xb00ab29b,0x32e83084,0x20e82f64,0xb3feb318,0x2d8da597,0x338133f8,
  0xb1fcae48,0xb14fb35c,0x339031b8,0x2d3a3199,0xb3e6b3ae,0x2909ac7b,0x32d133f4,0xb030a6f5,0x319d33bf,0xb1b3ac02,0x2e3ca874,0x335e33ec,
  0xacc32b89,0xb3a3b3c6,0x33f83276,0x25c930b7,0xb3dcb1f8,0xaa01b154,0x30653335,0xb2b0aef4,0xb107b383,0x32392d81,0xafa6214d,0xb307b3fe,
  0x30bc33a5,0xb273acb7,0x33c5311b,0x2ba23229,0xb0cc94b6,0xb267b400,0x30153360,0xb2e1ae31,0xb385b3ab,0x2d76ac93,0xb166a691,0xb1e7b3f5,
  0x22deb06a,0x33fd32ac,0xb337b3da,0x2ee8aa19,0x2f853387,0xb310ad6a,0x322d33fe,0xb1162216,0xb2a9abd3,0xb06fb3c2,0xb07428a6,0xb2a5b3ea,
  0xb111b3e9,0x323128be,0xb30db3c3,0x2f90abba,0x31aa227a,0x31a633fd,0x2e25ad5e,0x33633389,0x2d6a3365,0xb387ae1a,0xa21631aa,0xb3feb1a6,
  0xb3c2af85,0xabd3b310,0xb3eab22d,0x28a6b116,0xa8beb2a9,0x33e9306f,0x2bbab074,0x33c332a5,0x33fd3111,0x227a3231,0x3389330d,0xad5e2f90,
  0x2a63333f,0xb3d7aec6,0xb2a2a1b1,0xb07ab3fe,0xb3f7b158,0x25fbb1f4,0xacb7b38b,0x33a52d52,0x2e0eb025,0x336832d8,0x340030bc,0x14b63273,
  0x323533c0,0xb10c2beb,0xac9330cc,0xb3abb267,0x23433316,0xb3fdaf6f,0xb38eb225,0x2d46b11f,0xb342b29e,0x2ebbb07f,0x31e3aa7c,0x316b33d6,
  0x3264a6c3,0x30d133f5,0x2c0233ac,0xb3bfac87,0x28f0336a,0xb3e7ae02,0xb3c6b19d,0x2b89b1b3,0xa59732e8,0xb3f8b00a,0xaccfb3ed,0x33a1285b,
  0xb1b8b381,0x3199ad8d,0x336c31df,0xadf73170,0x33f42d3a,0x26f53390,0xb30423a7,0xafb2b3fc,0xb05f3030,0xb2b3b2d1,0x29e8b27a,0x33dd30b2,
  0xab5932b6,0xb3c9b05a,0x30adb089,0x327e3297,0xaf0ab3f3,0x332fa727,0x240633b0,0xb3fcac6f,0x33473194,0xaea431bc,0xb174b359,0x31daae54,
  0xb3bca565,0xac1ab3f9,0x33ee2f59,0xa842331b,0xaddf3281,0xb371b0a8,0x34002b40,0x1c5233cb,0xa759b3ef,0x33f22829,0xb2fe2c26,0xafc8b3ba,
  0x308e337c,0xb2932da5,0x3055b179,0x32ba31d6,0xb31eb146,0x2f4eb204,0xa5333394,0xb3f9ad23,0xaff33249,0xb2f1b0f3,0x30e532fb,0xb2542fd2,
  0x2b28b373,0x33cc2dd4,0xb285b18b,0x30a3b1c5,0x246a33fa,0xb3fba500,0x33962f42,0xad173321,0xadb1b3d0,0x337aaade,0xb3ffa99e,0x1f76b3e0,
  0xb0ee320d,0xb24db13c,0xac4b3398,0xb3b5ad0b,0x304ab289,0x32c1309e,0x2985b3ce,0x33e12b0f,0xaf3732f4,0xb324afe8,0xa4ce33f0,0xb3faa7ef,
  0x2dc8b34f,0x33762e82,0x9de4b3ff,0x33ff1ead,0xb1c931cd,0xb186b182,0xb3762e82,0xadc8b34f,0x324db13c,0x30ee320d,0x33b5ad0b,0x2c4b3398,
  0xb2c1309e,0xb04ab289,0xb3e12b0f,0xa985b3ce,0x3324afe8,0x2f3732f4,0x33faa7ef,0x24ce33f0,0xb285318b,0xb0a3b1c5,0xb2c7ae6b,0x3040b354,
  0x3396af42,0x2d173321,0x31413133,0xb2093215,0xb3ff299e,0x9f76b3e0,0xae8db2bd,0x334cb050,0x33b8278b,0xac3233f2,0x281033b3,0xb3ef2c57,
  0xb31e3146,0xaf4eb204,0xa533b394,0x33f9ad23,0x3400ab40,0x9c5233cb,0xae5f33e4,0xb357a93b,0xb2feac26,0x2fc8b3ba,0x3245b258,0x30f830e0,
  0x30553179,0xb2ba31d6,0xb3df2e99,0xa9b6b34a,0xb39230fd,0xad2fb241,0x3200b301,0x314a2fbd,0x337f1b11,0xad993400,0xb3ff2deb,0xa084b36f,
  0xb005b129,0x32ebb21d,0x325c2cdb,0xb0db339f,0xa92233de,0xb3e529cf,0xab59b2b6,0x33c9b05a,0xb3dd30b2,0xa9e8b27a,0x33d4ab71,0xaa9433c8,
  0x32212c0e,0xb12433bd,0xaf64b0d6,0x3318b260,0x197fb345,0x3400aeaf,0xae4833fe,0xb35c20e8,0xb23d3332,0xb102aeff,0x33aeb14f,0x2c7b31fc,
  0xb3fe3065,0xa14db2b0,0x2ebb307f,0xb342329e,0x300f2fa6,0xb2e53307,0x30d1b3f5,0x326426c3,0x302ab400,0x32d517db,0xb3e72e02,0x28f0b36a,
  0xb3fd2f6f,0x2343b316,0x2d46311f,0xb38e3225,0xb3f53015,0x2691b2e1,0xaf9b33eb,0xb30a288d,0x2a193166,0xb3da31e7,0x33d7aec6,0xaa63333f,
  0x3313b337,0x2f7a2ee8,0xa5fbb1f4,0x33f7b158,0xb1a1a8d7,0x31afb3e8,0xb36832d8,0xae0eb025,0xb3c22f85,0x2bd3b310,0xb3ea322d,0xa8a6b116,
  0xa8be32a9,0xb3e9306f,0x2bba3074,0xb3c332a5,0x33fdb111,0xa27a3231,0x3389b30d,0x2d5e2f90,0xa216b1aa,0x33feb1a6,0xaed2ae25,0x333db363,
  0xb3652edd,0x2e1ab33a,0xb1aa227a,0x31a6b3fd,0xaf853387,0xb3102d6a,0xb22d33fe,0xb116a216,0x32a9abd3,0xb06f33c2,0x307428a6,0xb2a533ea,
  0x3111b3e9,0x3231a8be,0x330db3c3,0x2f902bba,0xb2e12e31,0x3015b360,0x288db1a1,0x33ebb1af,0xb1e733f5,0xb1662691,0xb33f2f9b,0x2ec6b30a,
  0x2ee82a19,0xb33733da,0xb15833d7,0xb1f42a63,0x33e8b313,0x28d72f7a,0x302525fb,0xb2d833f7,0xb2392d81,0x3107b383,0x3307b3fe,0x2fa6214d,
  0xb35e33ec,0xae3ca874,0x97dbb00f,0x3400b2e5,0xa5c930b7,0xb3f83276,0xb316302a,0x2f6fb2d5,0x32b0aef4,0xb0653335,0xb29e33fd,0xb07f2343,
  0xb1702ccf,0x31dfb3a1,0x3345b124,0xaeaf3221,0xb3fc336c,0xa3a7adf7,0x3332b400,0x2eff997f,0xb0b23304,0xb27a2fb2,0x2b71b102,0x33c8b23d,
  0x2c0e29e8,0xb3bd33dd,0xb0d62a94,0x3260b3d4,0xb0892c1a,0x3297b3bc,0x2aad2842,0xb3d333ee,0xb3b0327e,0x2c6fb0ad,0x3241b035,0xb0fd32ce,
  0xb35933fc,0xae542406,0x3400b392,0x1b112d2f,0xaf5931da,0xb31b3174,0x321db37f,0x3129ad99,0xaf152ac6,0x332cb3d2,0xb1463293,0xb204308e,
  0xb281312e,0x30a8b219,0xab402f4e,0xb3cb331e,0xb3ef3371,0x2829addf,0x2c269c52,0xb3ba3400,0xb37c33f2,0xada52759,0x3179afc8,0xb1d632fe,
  0xacf32953,0x339cb3e3,0xb3fa33cc,0x2500ab28,0xb0942f21,0x3290b32a,0xb3d033fb,0xaade246a,0xb249317d,0x30f3b1d2,0xb2fb337a,0xafd22db1,
  0xb37332f1,0x2dd4aff3,0xb18b3254,0xb1c530e5,0xa96c27bd,0x33e2b3f1,0xb0452fdd,0x32c4b2f7,0xac3e2af7,0x33b7b3cf,0xb0ea3099,0x3250b28c,
  0xadbc2cff,0x3378b39a,0xb1823137,0x31cdb211,0xaf2c2e76,0x3327b352,0xb20d31c9,0x313cb186,0x313c3186,0xb20db1c9,0x2d0b2dc8,0xb398b376,
  0x309e30ee,0xb289b24d,0x2b0f2c4b,0xb3ceb3b5,0x2fe8304a,0xb2f4b2c1,0x27ef2985,0xb3f0b3e1,0x2e822f37,0xb34fb324,0x1ead24ce,0xb3ffb3fa,
  0xb2bdb209,0xb050b141,0xb290b32a,0x30942f21,0xb3b3b34c,0xac57ae8d,0xb0f3b1d2,0x3249317d,0xb400b3ef,0x1d1ba810,0xadd4aff3,0x337332f1,
  0xb39cb3e3,0x2cf32953,0xa500ab28,0x33fa33cc,0xae99b0f8,0x334a3245,0x33ff33b2,0x201f2c63,0x2438a9b6,0x33fc33df,0x332c33d2,0xaf15aac6,
  0x303a2ce7,0x32cb339e,0x30a83219,0xb281b12e,0x32ee31c0,0x2ffe3190,0x28292ddf,0xb3efb371,0x33b0327e,0x2c6f30ad,0xb241b035,0xb0fdb2ce,
  0x335933fc,0xae54a406,0xb400b392,0x1b11ad2f,0x2f5931da,0xb31bb174,0xb21db37f,0x31292d99,0xaaad2842,0xb3d3b3ee,0xa9cfb005,0x33de32eb,
  0x285b305f,0xb3edb2b3,0x2c0ea9e8,0x33bd33dd,0xb170accf,0xb1dfb3a1,0x33453124,0x2eaf3221,0xb3fcb36c,0x23a7adf7,0x33323400,0xaeff997f,
  0xb0b2b304,0x327a2fb2,0x2b713102,0xb3c8b23d,0xb400b2e5,0x17dbb00f,0x2e023264,0xb36ab0d1,0xaf6fb2d5,0x3316302a,0xb11fa8f0,0xb225b3e7,
  0x307f2343,0x329e33fd,0xb3d6b38e,0x2a7cad46,0x33f53342,0xa6c32ebb,0xac87b1e3,0x33ac316b,0x28d7af7a,0x33e83313,0xb2d8b3f7,0x3025a5fb,
  0x33eb31af,0x288d31a1,0x2bebae0e,0x33c03368,0x2ec6330a,0xb33faf9b,0x33fe3235,0x21b1310c,0xb1f4aa63,0xb158b3d7,0x2d5232a2,0xb38bb07a,
  0x33a7333d,0xacab2ed2,0x33f63162,0x262d31eb,0xaa4b301a,0xb3d8b2de,0x2a32326b,0xb3d9b0c7,0xb3f6b26f,0x265fb0c1,0xb3a9b020,0xac9fb2db,
  0x0e48b15d,0x340031f0,0xae1ab33a,0x33652edd,0xaed22e25,0xb33db363,0xb1eb0e48,0xb162b400,0xb2deb3a7,0x301aacab,0xb0c7b3f6,0x326b262d,
  0x30c1aa4b,0x326f33d8,0x32db2a32,0x302033d9,0x31f033f6,0xb15d265f,0x2edd33a9,0xb33aac9f,0xb2acb385,0x306aad76,0x2a19b166,0x33da31e7,
  0x3229a2de,0x311b33fd,0x33133337,0xaf7a2ee8,0x2e3133c5,0xb360aba2,0xb1a128d7,0xb1afb3e8,0xb3f5b015,0xa691b2e1,0xaf9bb3eb,0x330a288d,
  0x3154acc3,0x31f833a3,0x2ef433f8,0xb335a5c9,0x2d8133dc,0xb383aa01,0xb3feb065,0x214db2b0,0xb3ecb107,0x2874b239,0x300fafa6,0x32e53307,
  0x30b7ae3c,0x3276335e,0x302a3400,0xb2d517db,0x312433bd,0xb2212c0e,0xb318b260,0x2f64b0d6,0xb400aeaf,0x997fb345,0x335c20e8,0x2e4833fe,
  0x3102aeff,0x323d3332,0xac7b31fc,0xb3aeb14f,0x2a9433c8,0xb3d4ab71,0xb084b3e6,0x329ba909,0xb2ce2aad,0xb035b3d3,0x33e529cf,0x292233de,
  0x2d2fb241,0x339230fd,0xb14a2fbd,0xb200b301,0x2d993400,0xb37f1b11,0x2084b36f,0x33ff2deb,0xb2ebb21d,0x3005b129,0x30db339f,0xb25c2cdb,
  0xae5fb3e4,0x3357a93b,0xb190303a,0xb1c0b2cb,0x32453258,0xb0f830e0,0x2c63b2ee,0x33b22ffe,0xb3dfae99,0x29b6b34a,0x2ac633ff,0xb3d2a01f,
  0x339ea438,0x2ce733fc,0xb12eb32c,0x3219af15,0x33b8a78b,0x2c3233f2,0x2810b3b3,0x33ef2c57,0xb2c72e6b,0xb040b354,0x29533400,0xb3e31d1b,
  0x3141b133,0x32093215,0xaf21b39c,0x332aacf3,0xae8d32bd,0xb34cb050,0x317d3290,0xb1d23094,0x27bd33fb,0xb3f1249c,0x2fdd3327,0xb2f72f2c,
  0xaaf7b3e2,0x33cfa96c,0xb099b2c4,0x328cb045,0x2cff33b7,0xb39a2c3e,0x31373250,0xb21130ea,0xae76b378,0x3352adbc,0xb1c9b1cd,0x3186b182,
  0xb3ff1ead,0x1de4b3ff,0xb352adbc,0x2e76b378,0x33f1249c,0xa7bd33fb,0x32f72f2c,0xafdd3327,0xb3cfa96c,0x2af7b3e2,0xb28cb045,0x3099b2c4,
  0x339a2c3e,0xacff33b7,0x321130ea,0xb1373250,0x2953b400,0x33e31d1b,0x33ccadd4,0x2b283373,0xaf21339c,0xb32aacf3,0xb3fb2500,0x246ab3fa,
  0x317db290,0x31d23094,0x337a2ade,0xadb133d0,0xb2f130f3,0xaff3b249,0xb254afd2,0x30e5b2fb,0x339e2438,0xace733fc,0xb12e332c,0xb219af15,
  0xb190b03a,0x31c0b2cb,0x3371b0a8,0x2ddf3281,0x2c6332ee,0xb3b22ffe,0xb3f22829,0x2759b3ef,0x2ac6b3ff,0x33d2a01f,0x32932da5,0xb08e337c,
  0xaf0a33f3,0xb32fa727,0x2406b3b0,0x33fcac6f,0x3347b194,0x2ea431bc,0xb1743359,0xb1daae54,0xb3bc2565,0x2c1ab3f9,0x33eeaf59,0x2842331b,
  0x30ad3089,0xb27e3297,0xb2ceaaad,0x3035b3d3,0xb29ba909,0x3084b3e6,0x305f3030,0xb2b332d1,0x259732e8,0xb3f8300a,0x2ccfb3ed,0x33a1a85b,
  0x31b8b381,0x31992d8d,0xb36c31df,0xadf7b170,0xb3f42d3a,0x26f5b390,0x330423a7,0xafb233fc,0x316bb3d6,0x31e32a7c,0xb3832a01,0x2d81b3dc,
  0xb3bf2c87,0x2c02b3ac,0x28743239,0xb3ec3107,0x2b8931b3,0xb3c6319d,0x3276b35e,0x30b72e3c,0x31f8b3a3,0x31542cc3,0xb33525c9,0x2ef4b3f8,
  0x310c2beb,0xb23533c0,0x33abb267,0x2c9330cc,0x307ab3fe,0x32a2a1b1,0xb06aad76,0x32acb385,0xb3a52d52,0x2cb7b38b,0xb11b33fd,0xb229a2de,
  0x94b63273,0xb40030bc,0x3360aba2,0xae3133c5,0xb2de33a7,0xb01aacab,0xb0c733f6,0xb26b262d,0x30c12a4b,0xb26f33d8,0x32dbaa32,0xb02033d9,
  0x31f0b3f6,0x315d265f,0x2eddb3a9,0x333aac9f,0xb1eb8e48,0x3162b400,0xb3872e1a,0x2d6ab365,0xae25ad5e,0x3363b389,0x8e48b15d,0x3400b1f0,
  0xb3a7333d,0xacabaed2,0xb3f63162,0x262db1eb,0x2a4b301a,0xb3d832de,0xaa32326b,0xb3d930c7,0x33f6b26f,0x265f30c1,0x33a9b020,0xac9f32db,
  0x33c0b368,0x2beb2e0e,0x30cc94b6,0xb2673400,0x21b1b10c,0x33feb235,0x3385b3ab,0x2d762c93,0xb38b307a,0x2d52b2a2,0xa2deb06a,0x33fdb2ac,
  0xb0bc33a5,0xb2732cb7,0xb3c5311b,0x2ba2b229,0x26c32ebb,0xb3f53342,0xb3ac316b,0x2c87b1e3,0x336ab0d1,0xae023264,0xb19d33bf,0xb1b32c02,
  0x3225b3e7,0x311fa8f0,0x2cc32b89,0xb3a333c6,0xaa7cad46,0x33d6b38e,0x33dcb1f8,0xaa013154,0xb3fe3318,0x20e8af64,0x3381b3f8,0x2d8d2597,
  0xb14f335c,0xb1fc2e48,0x2d3ab199,0x3390b1b8,0x29092c7b,0xb3e633ae,0xb03026f5,0x32d1b3f4,0x32e8b084,0xb00a329b,0xb3ed32b3,0x285bb05f,
  0x29cfb005,0x33deb2eb,0xb05a325c,0xb2b630db,0xafbd2922,0x3301b3e5,0x27272b59,0xb3f333c9,0xb36f3200,0x2debb14a,0x31bcaf0a,0xb194332f,
  0xb39f33ff,0xacdba084,0x33f9b347,0xa5652ea4,0x3394b2ba,0xad233055,0xa438a9b6,0x33fcb3df,0x33e4b3f9,0x293b2533,0xb03a2ce7,0x32cbb39e,
  0x3258b357,0x30e0ae5f,0xb2ee31c0,0x2ffeb190,0x2e99b0f8,0x334ab245,0xb3ff33b2,0x201fac63,0xaf4230a3,0xb3213285,0x3133b040,0xb21532c7,
  0xa99e2d17,0xb3e03396,0x32bdb209,0xb0503141,0x278b1f76,0xb3f233ff,0x33b3b34c,0xac572e8d,0x2e6bac32,0xb35433b8,0x3400b3ef,0x1d1b2810,
  0xb289324d,0x309eb0ee,0xb3ce33b5,0x2b0fac4b,0xb2f432c1,0x2fe8b04a,0xb3f033e1,0x27efa985,0xb34f3324,0x2e82af37,0xb3ff33fa,0x1eada4ce,
  0xb3983376,0x2d0badc8,0xb3fb33ff,0xa49c1de4,0x351c35f6,0xac93a617,0xb8a3b93c,0x308d2a16,0x32f43448,0xb160afa5,0xb6a4b7fe,0x353a3389,
  0x2fa53160,0xb448b2f4,0xb389b53a,0x37fe36a4,0x26172c93,0xb5f6b51c,0xaa16b08d,0x393c38a3,0x34c3358c,0xac47a5b2,0xb85fb8f3,0x304229b1,
  0x327e33fd,0xb106af26,0xb63cb785,0x34e7330f,0x2f263106,0xb3fdb27e,0xb30fb4e7,0x3785363c,0x25b22c47,0xb58cb4c3,0xa9b1b042,0x38f3385f,
  0x346a3523,0xabf6a54d,0xb81ab8a8,0x2fef294d,0x3209336b,0xb0acaea7,0xb5d4b70a,0x34933294,0x2ea730ac,0xb36bb209,0xb294b493,0x370a35d4,
  0x254d2bf6,0xb523b46a,0xa94dafef,0x38a8381a,0x341334bc,0xab5fa4e9,0xb7a6b85a,0x2f5928e8,0x319432da,0xb052ae28,0xb56ab68d,0x343e3219,
  0x2e283052,0xb2dab194,0xb219b43e,0x368d356a,0x24e92b5f,0xb4bcb413,0xa8e8af59,0x385a37a6,0x33783456,0xaac8a484,0xb715b80a,0x2ec32884,
  0x3120324a,0xaff2ada9,0xb4ffb60e,0x33d3319e,0x2da92ff2,0xb24ab120,0xb19eb3d3,0x360e34ff,0x24842ac8,0xb456b378,0xa884aec3,0x380a3715,
  0x32cd33e3,0xaa31a420,0xb682b76f,0x2e2d281f,0x30ac31bb,0xaf3fad2a,0xb493b58d,0x33283122,0x2d2a2f3f,0xb1bbb0ac,0xb122b328,0x358d3493,
  0x24202a31,0xb3e3b2cd,0xa81fae2d,0x376f3682,0x3223331c,0xa999a376,0xb5ebb6c6,0x2d972776,0x3039312d,0xae8dacac,0xb426b50b,0x327c30a6,
  0x2cac2e8d,0xb12db039,0xb0a6b27c,0x350b3426,0x23762999,0xb31cb223,0xa776ad97,0x36c635eb,0x317a3257,0xa902a2ad,0xb552b61a,0x2d0026ad,
  0x2f8c309f,0xaddcac2e,0xb371b487,0x31cf3029,0x2c2e2ddc,0xb09faf8c,0xb029b1cf,0x34873371,0x22ad2902,0xb257b17a,0xa6adad00,0x361a3552,
  0x30d23194,0xa86ba1e4,0xb4b7b56a,0x2c6a25e4,0x2ea73012,0xad2aab5f,0xb294b402,0x31222f59,0x2b5f2d2a,0xb012aea7,0xaf59b122,0x34023294,
  0x21e4286b,0xb194b0d2,0xa5e4ac6a,0x356a34b7,0x302c30d2,0xa7a9a11b,0xb41ab4b7,0x2ba7251b,0x2dc22f0c,0xac79aa63,0xb1b6b2f7,0x30742e5f,
  0x2a632c79,0xaf0cadc2,0xae5fb074,0x32f731b6,0x211b27a9,0xb0d2b02c,0xa51baba7,0x34b7341a,0x2f0c3012,0xa67ba052,0xb2f7b402,0x2a7a2452,
  0x2cde2df5,0xab91a967,0xb0d7b1e8,0x2f8b2d65,0x29672b91,0xadf5acde,0xad65af8b,0x31e830d7,0x2052267b,0xb012af0c,0xa452aa7a,0x340232f7,
  0x2dc22ea7,0xa54d9f12,0xb1b6b294,0x294d2311,0x2bf62cde,0xaa31a86b,0xafefb0d7,0x2e2d2c6a,0x286b2a31,0xacdeabf6,0xac6aae2d,0x30d72fef,
  0x1f12254d,0xaea7adc2,0xa311a94d,0x329431b6,0x2c792d2a,0xa4209d7f,0xb074b122,0x281f217f,0x2a312b91,0xa8d0a6e0,0xae2daf8b,0x2cce2ade,
  0x26e028d0,0xab91aa31,0xaadeacce,0x2f8b2e2d,0x1d7f2420,0xad2aac79,0xa17fa81f,0x31223074,0x2a632b5f,0xa1e49bdb,0xae5faf59,0x25e41fdb,
  0x286b2967,0xa6e0a4e9,0xac6aad65,0x2ade28e8,0x24e926e0,0xa967a86b,0xa8e8aade,0x2d652c6a,0x1bdb21e4,0xab5faa63,0x9fdba5e4,0x2f592e5f,
  0x27a9286b,0x9f1298b6,0xaba7ac6a,0x23111cb6,0x254d267b,0xa420a1e4,0xa94daa7a,0x281f25e4,0x21e42420,0xa67ba54d,0xa5e4a81f,0x2a7a294d,
  0x18b61f12,0xa86ba7a9,0x9cb6a311,0x2c6a2ba7,0x211b21e4,0x98b69248,0xa51ba5e4,0x1cb61648,0x1f122052,0x9d7f9bdb,0xa311a452,0x217f1fdb,
  0x1bdb1d7f,0xa0529f12,0x9fdba17f,0x24522311,0x124818b6,0xa1e4a11b,0x96489cb6,0x25e4251b,0xa11ba1e4,0x18b61248,0x251b25e4,0x9cb69648,
  0x9f12a052,0x1d7f1bdb,0x23112452,0xa17f9fdb,0x9bdb9d7f,0x20521f12,0x1fdb217f,0xa452a311,0x924898b6,0x21e4211b,0x16481cb6,0xa5e4a51b,
  0xa7a9a86b,0x1f1218b6,0x2ba72c6a,0xa3119cb6,0xa54da67b,0x242021e4,0x294d2a7a,0xa81fa5e4,0xa1e4a420,0x267b254d,0x25e4281f,0xaa7aa94d,
  0x98b69f12,0x286b27a9,0x1cb62311,0xac6aaba7,0xaa63ab5f,0x21e41bdb,0x2e5f2f59,0xa5e49fdb,0xa86ba967,0x26e024e9,0x2c6a2d65,0xaadea8e8,
  0xa4e9a6e0,0x2967286b,0x28e82ade,0xad65ac6a,0x9bdba1e4,0x2b5f2a63,0x1fdb25e4,0xaf59ae5f,0xac79ad2a,0x24201d7f,0x30743122,0xa81fa17f,
  0xaa31ab91,0x28d026e0,0x2e2d2f8b,0xacceaade,0xa6e0a8d0,0x2b912a31,0x2ade2cce,0xaf8bae2d,0x9d7fa420,0x2d2a2c79,0x217f281f,0xb122b074,
  0xadc2aea7,0x254d1f12,0x31b63294,0xa94da311,0xabf6acde,0x2a31286b,0x2fef30d7,0xae2dac6a,0xa86baa31,0x2cde2bf6,0x2c6a2e2d,0xb0d7afef,
  0x9f12a54d,0x2ea72dc2,0x2311294d,0xb294b1b6,0xaf0cb012,0x267b2052,0x32f73402,0xaa7aa452,0xacdeadf5,0x2b912967,0x30d731e8,0xaf8bad65,
  0xa967ab91,0x2df52cde,0x2d652f8b,0xb1e8b0d7,0xa052a67b,0x30122f0c,0x24522a7a,0xb402b2f7,0xb02cb0d2,0x27a9211b,0x341a34b7,0xaba7a51b,
  0xadc2af0c,0x2c792a63,0x31b632f7,0xb074ae5f,0xaa63ac79,0x2f0c2dc2,0x2e5f3074,0xb2f7b1b6,0xa11ba7a9,0x30d2302c,0x251b2ba7,0xb4b7b41a,
  0xb0d2b194,0x286b21e4,0x34b7356a,0xac6aa5e4,0xaea7b012,0x2d2a2b5f,0x32943402,0xb122af59,0xab5fad2a,0x30122ea7,0x2f593122,0xb402b294,
  0xa1e4a86b,0x319430d2,0x25e42c6a,0xb56ab4b7,0xb17ab257,0x290222ad,0x3552361a,0xad00a6ad,0xaf8cb09f,0x2ddc2c2e,0x33713487,0xb1cfb029,
  0xac2eaddc,0x309f2f8c,0x302931cf,0xb487b371,0xa2ada902,0x3257317a,0x26ad2d00,0xb61ab552,0xb223b31c,0x29992376,0x35eb36c6,0xad97a776,
  0xb039b12d,0x2e8d2cac,0x3426350b,0xb27cb0a6,0xacacae8d,0x312d3039,0x30a6327c,0xb50bb426,0xa376a999,0x331c3223,0x27762d97,0xb6c6b5eb,
  0xb2cdb3e3,0x2a312420,0x3682376f,0xae2da81f,0xb0acb1bb,0x2f3f2d2a,0x3493358d,0xb328b122,0xad2aaf3f,0x31bb30ac,0x31223328,0xb58db493,
  0xa420aa31,0x33e332cd,0x281f2e2d,0xb76fb682,0xb378b456,0x2ac82484,0x3715380a,0xaec3a884,0xb120b24a,0x2ff22da9,0x34ff360e,0xb3d3b19e,
  0xada9aff2,0x324a3120,0x319e33d3,0xb60eb4ff,0xa484aac8,0x34563378,0x28842ec3,0xb80ab715,0xb413b4bc,0x2b5f24e9,0x37a6385a,0xaf59a8e8,
  0xb194b2da,0x30522e28,0x356a368d,0xb43eb219,0xae28b052,0x32da3194,0x3219343e,0xb68db56a,0xa4e9ab5f,0x34bc3413,0x28e82f59,0xb85ab7a6,
  0xb46ab523,0x2bf6254d,0x381a38a8,0xafefa94d,0xb209b36b,0x30ac2ea7,0x35d4370a,0xb493b294,0xaea7b0ac,0x336b3209,0x32943493,0xb70ab5d4,
  0xa54dabf6,0x3523346a,0x294d2fef,0xb8a8b81a,0xb4c3b58c,0x2c4725b2,0x385f38f3,0xb042a9b1,0xb27eb3fd,0x31062f26,0x363c3785,0xb4e7b30f,
  0xaf26b106,0x33fd327e,0x330f34e7,0xb785b63c,0xa5b2ac47,0x358c34c3,0x29b13042,0xb8f3b85f,0xb51cb5f6,0x2c932617,0x38a3393c,0xb08daa16,
  0xb2f4b448,0x31602fa5,0x36a437fe,0xb53ab389,0xafa5b160,0x344832f4,0x3389353a,0xb7feb6a4,0xa617ac93,0x35f6351c,0x2a16308d,0xb93cb8a3,
};
__device__ __align__(128) const uint32_t c_img[2560] = {
  0x326d31ed,0x333b32dd,0x33c33388,0x33fe33ea,0x33c331ed,0x31ed33c3,0xa8b22d64,0xb33bb0c4,0x33ea31ed,0xad64301d,0xb2ddb388,0x315fa8b2,
  0x32dd31ed,0xb3feabc6,0x326dad64,0xad64326d,0x30c431ed,0xaed7b2dd,0x2bc63388,0xa248b3ea,0x2bc631ed,0x315fb3c3,0xb3ea2d64,0x2ed730c4,
  0xa8b231ed,0x3388b01d,0x301db388,0xb1ed28b2,0xb01d31ed,0x22482bc6,0x30c4ad64,0x3388b26d,0x33ea33fe,0x338833c3,0x32dd333b,0x31ed326d,
  0xb2ddb3fe,0xa248b01d,0x326d2ed7,0x338833ea,0x30c433fe,0xb33babc6,0xabc6b33b,0x33fe30c4,0xabc6b3fe,0x31ed32dd,0xb3eaaed7,0x333ba8b2,
  0xa8b233fe,0x2d64b3c3,0xb01d333b,0x315fb26d,0x301db3fe,0xb3fe301d,0x30c42ed7,0x2d64b3ea,0xb26d33fe,0x2ed72bc6,0x33c3b33b,0xa248b0c4,
  0x33c3b3fe,0x315fb2dd,0x28b2aed7,0xaed728b2,0xb0c4b15f,0xaed7b01d,0xabc6ad64,0xa248a8b2,0xabc6b15f,0x315f2bc6,0x33ea3388,0x2ed7326d,
  0x28b2b15f,0x338832dd,0xb01d2d64,0xb1edb3ea,0x301db15f,0x224833c3,0xb0c4b388,0x338830c4,0x326db15f,0xb33b301d,0x33c3ad64,0xb3fe28b2,
  0x33c3b15f,0xb1edabc6,0xa8b23388,0x333bb26d,0x33eab15f,0x2d64b2dd,0xb2dd2d64,0xb15f33ea,0x32ddb15f,0x33feb3c3,0x326db388,0x2d64b0c4,
  0x28b22248,0x2d642bc6,0x301d2ed7,0x315f30c4,0xb01da248,0xb3feb2dd,0xb0c4b33b,0x2d64a8b2,0x326d2248,0x2ed733c3,0xb3c3aed7,0xa248b26d,
  0xb3c3a248,0x315fb01d,0xa8b2333b,0xaed7b3ea,0x33ea2248,0xb388abc6,0x32dd2ed7,0xb1edb0c4,0xb2dda248,0x224832dd,0x326db33b,0xb38828b2,
  0x30c42248,0x333bb3c3,0xabc6aed7,0xb3fe326d,0xabc6a248,0xb1ed301d,0xb3ea333b,0xb33b33ea,0xb26d31ed,0xb33b32dd,0xb3c33388,0xb3fe33ea,
  0xb3c331ed,0xb1ed33c3,0x28b22d64,0x333bb0c4,0xb3ea31ed,0x2d64301d,0x32ddb388,0xb15fa8b2,0xb2dd31ed,0x33feabc6,0xb26dad64,0x2d64326d,
  0xb0c431ed,0x2ed7b2dd,0xabc63388,0x2248b3ea,0xabc631ed,0xb15fb3c3,0x33ea2d64,0xaed730c4,0x28b231ed,0xb388b01d,0xb01db388,0x31ed28b2,
  0x301d31ed,0xa2482bc6,0xb0c4ad64,0xb388b26d,0xb3ea33fe,0xb38833c3,0xb2dd333b,0xb1ed326d,0x32ddb3fe,0x2248b01d,0xb26d2ed7,0xb38833ea,
  0xb0c433fe,0x333babc6,0x2bc6b33b,0xb3fe30c4,0x2bc6b3fe,0xb1ed32dd,0x33eaaed7,0xb33ba8b2,0x28b233fe,0xad64b3c3,0x301d333b,0xb15fb26d,
  0xb01db3fe,0x33fe301d,0xb0c42ed7,0xad64b3ea,0x326d33fe,0xaed72bc6,0xb3c3b33b,0x2248b0c4,0xb3c3b3fe,0xb15fb2dd,0xa8b2aed7,0x2ed728b2,
  0x30c4b15f,0x2ed7b01d,0x2bc6ad64,0x2248a8b2,0x2bc6b15f,0xb15f2bc6,0xb3ea3388,0xaed7326d,0xa8b2b15f,0xb38832dd,0x301d2d64,0x31edb3ea,
  0xb01db15f,0xa24833c3,0x30c4b388,0xb38830c4,0xb26db15f,0x333b301d,0xb3c3ad64,0x33fe28b2,0xb3c3b15f,0x31edabc6,0x28b23388,0xb33bb26d,
  0xb3eab15f,0xad64b2dd,0x32dd2d64,0x315f33ea,0xb2ddb15f,0xb3feb3c3,0xb26db388,0xad64b0c4,0xa8b22248,0xad642bc6,0xb01d2ed7,0xb15f30c4,
  0x301da248,0x33feb2dd,0x30c4b33b,0xad64a8b2,0xb26d2248,0xaed733c3,0x33c3aed7,0x2248b26d,0x33c3a248,0xb15fb01d,0x28b2333b,0x2ed7b3ea,
  0xb3ea2248,0x3388abc6,0xb2dd2ed7,0x31edb0c4,0x32dda248,0xa24832dd,0xb26db33b,0x338828b2,0xb0c42248,0xb33bb3c3,0x2bc6aed7,0x33fe326d,
  0x2bc6a248,0x31ed301d,0x33ea333b,0x333b33ea,0x30c4315f,0x2ed7301d,0x2bc62d64,0x224828b2,0x2bc6315f,0xb15fabc6,0xb3eab388,0xaed7b26d,
  0xa8b2315f,0xb388b2dd,0x301dad64,0x31ed33ea,0xb01d315f,0xa248b3c3,0x30c43388,0xb388b0c4,0xb26d315f,0x333bb01d,0xb3c32d64,0x33fea8b2,
  0xb3c3315f,0x31ed2bc6,0x28b2b388,0xb33b326d,0xb3ea315f,0xad6432dd,0x32ddad64,0x315fb3ea,0xb2dd315f,0xb3fe33c3,0xb26d3388,0xad6430c4,
  0xa8b2a248,0xad64abc6,0xb01daed7,0xb15fb0c4,0x301d2248,0x33fe32dd,0x30c4333b,0xad6428b2,0xb26da248,0xaed7b3c3,0x33c32ed7,0x2248326d,
  0x33c32248,0xb15f301d,0x28b2b33b,0x2ed733ea,0xb3eaa248,0x33882bc6,0xb2ddaed7,0x31ed30c4,0x32dd2248,0xa248b2dd,0xb26d333b,0x3388a8b2,
  0xb0c4a248,0xb33b33c3,0x2bc62ed7,0x33feb26d,0x2bc62248,0x31edb01d,0x33eab33b,0x333bb3ea,0x326d31ed,0x333b32dd,0x33c33388,0x33fe33ea,
  0x33c331ed,0x31ed33c3,0xa8b22d64,0xb33bb0c4,0x33ea31ed,0xad64301d,0xb2ddb388,0x315fa8b2,0x32dd31ed,0xb3feabc6,0x326dad64,0xad64326d,
  0x30c431ed,0xaed7b2dd,0x2bc63388,0xa248b3ea,0x2bc631ed,0x315fb3c3,0xb3ea2d64,0x2ed730c4,0xa8b231ed,0x3388b01d,0x301db388,0xb1ed28b2,
  0xb01d31ed,0x22482bc6,0x30c4ad64,0x3388b26d,0x33ea33fe,0x338833c3,0x32dd333b,0x31ed326d,0xb2ddb3fe,0xa248b01d,0x326d2ed7,0x338833ea,
  0x30c433fe,0xb33babc6,0xabc6b33b,0x33fe30c4,0xabc6b3fe,0x31ed32dd,0xb3eaaed7,0x333ba8b2,0xa8b233fe,0x2d64b3c3,0xb01d333b,0x315fb26d,
  0x301db3fe,0xb3fe301d,0x30c42ed7,0x2d64b3ea,0xb26d33fe,0x2ed72bc6,0x33c3b33b,0xa248b0c4,0x33c3b3fe,0x315fb2dd,0x28b2aed7,0xaed728b2,
  0xb0c4315f,0xaed7301d,0xabc62d64,0xa24828b2,0xabc6315f,0x315fabc6,0x33eab388,0x2ed7b26d,0x28b2315f,0x3388b2dd,0xb01dad64,0xb1ed33ea,
  0x301d315f,0x2248b3c3,0xb0c43388,0x3388b0c4,0x326d315f,0xb33bb01d,0x33c32d64,0xb3fea8b2,0x33c3315f,0xb1ed2bc6,0xa8b2b388,0x333b326d,
  0x33ea315f,0x2d6432dd,0xb2ddad64,0xb15fb3ea,0x32dd315f,0x33fe33c3,0x326d3388,0x2d6430c4,0x28b2a248,0x2d64abc6,0x301daed7,0x315fb0c4,
  0xb01d2248,0xb3fe32dd,0xb0c4333b,0x2d6428b2,0x326da248,0x2ed7b3c3,0xb3c32ed7,0xa248326d,0xb3c32248,0x315f301d,0xa8b2b33b,0xaed733ea,
  0x33eaa248,0xb3882bc6,0x32ddaed7,0xb1ed30c4,0xb2dd2248,0x2248b2dd,0x326d333b,0xb388a8b2,0x30c4a248,0x333b33c3,0xabc62ed7,0xb3feb26d,
  0xabc62248,0xb1edb01d,0xb3eab33b,0xb33bb3ea,0xb26d31ed,0xb33b32dd,0xb3c33388,0xb3fe33ea,0xb3c331ed,0xb1ed33c3,0x28b22d64,0x333bb0c4,
  0xb3ea31ed,0x2d64301d,0x32ddb388,0xb15fa8b2,0xb2dd31ed,0x33feabc6,0xb26dad64,0x2d64326d,0xb0c431ed,0x2ed7b2dd,0xabc63388,0x2248b3ea,
  0xabc631ed,0xb15fb3c3,0x33ea2d64,0xaed730c4,0x28b231ed,0xb388b01d,0xb01db388,0x31ed28b2,0x301d31ed,0xa2482bc6,0xb0c4ad64,0xb388b26d,
  0xb3ea33fe,0xb38833c3,0xb2dd333b,0xb1ed326d,0x32ddb3fe,0x2248b01d,0xb26d2ed7,0xb38833ea,0xb0c433fe,0x333babc6,0x2bc6b33b,0xb3fe30c4,
  0x2bc6b3fe,0xb1ed32dd,0x33eaaed7,0xb33ba8b2,0x28b233fe,0xad64b3c3,0x301d333b,0xb15fb26d,0xb01db3fe,0x33fe301d,0xb0c42ed7,0xad64b3ea,
  0x326d33fe,0xaed72bc6,0xb3c3b33b,0x2248b0c4,0xb3c3b3fe,0xb15fb2dd,0xa8b2aed7,0x2ed728b2,0x29ed29ed,0x29ed29ed,0x29ed29ed,0x29ed29ed,
  0x2bc32a6d,0x2add2bea,0x23c628c4,0xa81da0b2,0x2bc32add,0xa3c6281d,0xabc3aadd,0x23c6a81d,0x29ed2b3b,0xabfea564,0x295fa6d7,0x1a482b88,
  0x25642b88,0xa564ab88,0x25642b88,0xa564ab88,0xa0b22bc3,0x2a6daadd,0xabea23c6,0x28c4281d,0xa8c42bea,0x2a6da0b2,0x28c4abea,0xaa6d20b2,
  0xab3b2bfe,0xa564295f,0x26d79a48,0x2b88a9ed,0x29ed29ed,0x29ed29ed,0x29ed29ed,0x29ed29ed,0xabc3aa6d,0xaaddabea,0xa3c6a8c4,0x281d20b2,
  0x2bc32add,0xa3c6281d,0xabc3aadd,0x23c6a81d,0xa9edab3b,0x2bfe2564,0xa95f26d7,0x9a48ab88,0x25642b88,0xa564ab88,0x25642b88,0xa564ab88,
  0x20b2abc3,0xaa6d2add,0x2beaa3c6,0xa8c4a81d,0xa8c42bea,0x2a6da0b2,0x28c4abea,0xaa6d20b2,0x2b3babfe,0x2564a95f,0xa6d71a48,0xab8829ed,
  0x295f295f,0x295f295f,0x295f295f,0x295f295f,0x23c628c4,0xa81da0b2,0xabc3aa6d,0xaaddabea,0xa3c6281d,0xabc3aadd,0x23c6a81d,0x2bc32add,
  0xa95f26d7,0x9a48ab88,0x29ed2b3b,0xabfea564,0xab882564,0x2b88a564,0xab882564,0x2b88a564,0xabea23c6,0x28c4281d,0x20b2abc3,0xaa6d2add,
  0xaa6d20b2,0xa8c42bea,0x2a6da0b2,0x28c4abea,0xa6d71a48,0xab8829ed,0xab3b2bfe,0xa564295f,0x295f295f,0x295f295f,0x295f295f,0x295f295f,
  0xa3c6a8c4,0x281d20b2,0x2bc32a6d,0x2add2bea,0xa3c6281d,0xabc3aadd,0x23c6a81d,0x2bc32add,0x295fa6d7,0x1a482b88,0xa9edab3b,0x2bfe2564,
  0xab882564,0x2b88a564,0xab882564,0x2b88a564,0x2beaa3c6,0xa8c4a81d,0xa0b22bc3,0x2a6daadd,0xaa6d20b2,0xa8c42bea,0x2a6da0b2,0x28c4abea,
  0x26d79a48,0x2b88a9ed,0x2b3babfe,0x2564a95f,0xabfe2bfe,0xabfe2bfe,0xabfe2bfe,0xabfe2bfe,0xaadd2bea,0xa3c628c4,0x281da0b2,0x2bc3aa6d,
  0xa81d2bc3,0x2adda3c6,0x281dabc3,0xaadd23c6,0x9a482b88,0x29edab3b,0xabfe2564,0x295f26d7,0x26d72b3b,0xa6d7ab3b,0x26d72b3b,0xa6d7ab3b,
  0x2a6d2add,0xabeaa3c6,0x28c4a81d,0x20b22bc3,0x2bea2a6d,0xa0b228c4,0xabeaaa6d,0x20b2a8c4,0x2b8829ed,0x2b3b2bfe,0x2564295f,0xa6d79a48,
  0xabfe2bfe,0xabfe2bfe,0xabfe2bfe,0xabfe2bfe,0x2addabea,0x23c6a8c4,0xa81d20b2,0xabc32a6d,0xa81d2bc3,0x2adda3c6,0x281dabc3,0xaadd23c6,
  0x1a48ab88,0xa9ed2b3b,0x2bfea564,0xa95fa6d7,0x26d72b3b,0xa6d7ab3b,0x26d72b3b,0xa6d7ab3b,0xaa6daadd,0x2bea23c6,0xa8c4281d,0xa0b2abc3,
  0x2bea2a6d,0xa0b228c4,0xabeaaa6d,0x20b2a8c4,0xab88a9ed,0xab3babfe,0xa564a95f,0x26d71a48,0x1a489a48,0x1a489a48,0x1a489a48,0x1a489a48,
  0x281da0b2,0x2bc3aa6d,0x2addabea,0x23c6a8c4,0x2adda3c6,0x281dabc3,0xaadd23c6,0xa81d2bc3,0x2bfea564,0xa95fa6d7,0x9a482b88,0x29edab3b,
  0x2b3ba6d7,0xab3b26d7,0x2b3ba6d7,0xab3b26d7,0x28c4a81d,0x20b22bc3,0xaa6daadd,0x2bea23c6,0x20b2a8c4,0x2bea2a6d,0xa0b228c4,0xabeaaa6d,
  0xa564a95f,0x26d71a48,0x2b8829ed,0x2b3b2bfe,0x1a489a48,0x1a489a48,0x1a489a48,0x1a489a48,0xa81d20b2,0xabc32a6d,0xaadd2bea,0xa3c628c4,
  0x2adda3c6,0x281dabc3,0xaadd23c6,0xa81d2bc3,0xabfe2564,0x295f26d7,0x1a48ab88,0xa9ed2b3b,0x2b3ba6d7,0xab3b26d7,0x2b3ba6d7,0xab3b26d7,
  0xa8c4281d,0xa0b2abc3,0x2a6d2add,0xabeaa3c6,0x20b2a8c4,0x2bea2a6d,0xa0b228c4,0xabeaaa6d,0x2564295f,0xa6d79a48,0xab88a9ed,0xab3babfe,
  0xa95fa95f,0xa95fa95f,0xa95fa95f,0xa95fa95f,0xa3c6a8c4,0x281d20b2,0x2bc32a6d,0x2add2bea,0x23c6a81d,0x2bc32add,0xa3c6281d,0xabc3aadd,
  0x295fa6d7,0x1a482b88,0xa9edab3b,0x2bfe2564,0x2b88a564,0xab882564,0x2b88a564,0xab882564,0x2beaa3c6,0xa8c4a81d,0xa0b22bc3,0x2a6daadd,
  0x2a6da0b2,0x28c4abea,0xaa6d20b2,0xa8c42bea,0x26d79a48,0x2b88a9ed,0x2b3babfe,0x2564a95f,0xa95fa95f,0xa95fa95f,0xa95fa95f,0xa95fa95f,
  0x23c628c4,0xa81da0b2,0xabc3aa6d,0xaaddabea,0x23c6a81d,0x2bc32add,0xa3c6281d,0xabc3aadd,0xa95f26d7,0x9a48ab88,0x29ed2b3b,0xabfea564,
  0x2b88a564,0xab882564,0x2b88a564,0xab882564,0xabea23c6,0x28c4281d,0x20b2abc3,0xaa6d2add,0x2a6da0b2,0x28c4abea,0xaa6d20b2,0xa8c42bea,
  0xa6d71a48,0xab8829ed,0xab3b2bfe,0xa564295f,0x29ed29ed,0x29ed29ed,0x29ed29ed,0x29ed29ed,0x2bc32a6d,0x2add2bea,0x23c628c4,0xa81da0b2,
  0x2bc32add,0xa3c6281d,0xabc3aadd,0x23c6a81d,0x29ed2b3b,0xabfea564,0x295fa6d7,0x1a482b88,0x25642b88,0xa564ab88,0x25642b88,0xa564ab88,
  0xa0b22bc3,0x2a6daadd,0xabea23c6,0x28c4281d,0xa8c42bea,0x2a6da0b2,0x28c4abea,0xaa6d20b2,0xab3b2bfe,0xa564295f,0x26d79a48,0x2b88a9ed,
  0x29ed29ed,0x29ed29ed,0x29ed29ed,0x29ed29ed,0xabc3aa6d,0xaaddabea,0xa3c6a8c4,0x281d20b2,0x2bc32add,0xa3c6281d,0xabc3aadd,0x23c6a81d,
  0xa9edab3b,0x2bfe2564,0xa95f26d7,0x9a48ab88,0x25642b88,0xa564ab88,0x25642b88,0xa564ab88,0x20b2abc3,0xaa6d2add,0x2beaa3c6,0xa8c4a81d,
  0xa8c42bea,0x2a6da0b2,0x28c4abea,0xaa6d20b2,0x2b3babfe,0x2564a95f,0xa6d71a48,0xab8829ed,0x9a481a48,0x9a481a48,0x9a481a48,0x9a481a48,
  0xa81d20b2,0xabc32a6d,0xaadd2bea,0xa3c628c4,0xaadd23c6,0xa81d2bc3,0x2adda3c6,0x281dabc3,0xabfe2564,0x295f26d7,0x1a48ab88,0xa9ed2b3b,
  0xab3b26d7,0x2b3ba6d7,0xab3b26d7,0x2b3ba6d7,0xa8c4281d,0xa0b2abc3,0x2a6d2add,0xabeaa3c6,0xa0b228c4,0xabeaaa6d,0x20b2a8c4,0x2bea2a6d,
  0x2564295f,0xa6d79a48,0xab88a9ed,0xab3babfe,0x9a481a48,0x9a481a48,0x9a481a48,0x9a481a48,0x281da0b2,0x2bc3aa6d,0x2addabea,0x23c6a8c4,
  0xaadd23c6,0xa81d2bc3,0x2adda3c6,0x281dabc3,0x2bfea564,0xa95fa6d7,0x9a482b88,0x29edab3b,0xab3b26d7,0x2b3ba6d7,0xab3b26d7,0x2b3ba6d7,
  0x28c4a81d,0x20b22bc3,0xaa6daadd,0x2bea23c6,0xa0b228c4,0xabeaaa6d,0x20b2a8c4,0x2bea2a6d,0xa564a95f,0x26d71a48,0x2b8829ed,0x2b3b2bfe,
  0xabfe2bfe,0xabfe2bfe,0xabfe2bfe,0xabfe2bfe,0xaadd2bea,0xa3c628c4,0x281da0b2,0x2bc3aa6d,0xa81d2bc3,0x2adda3c6,0x281dabc3,0xaadd23c6,
  0x9a482b88,0x29edab3b,0xabfe2564,0x295f26d7,0x26d72b3b,0xa6d7ab3b,0x26d72b3b,0xa6d7ab3b,0x2a6d2add,0xabeaa3c6,0x28c4a81d,0x20b22bc3,
  0x2bea2a6d,0xa0b228c4,0xabeaaa6d,0x20b2a8c4,0x2b8829ed,0x2b3b2bfe,0x2564295f,0xa6d79a48,0xabfe2bfe,0xabfe2bfe,0xabfe2bfe,0xabfe2bfe,
  0x2addabea,0x23c6a8c4,0xa81d20b2,0xabc32a6d,0xa81d2bc3,0x2adda3c6,0x281dabc3,0xaadd23c6,0x1a48ab88,0xa9ed2b3b,0x2bfea564,0xa95fa6d7,
  0x26d72b3b,0xa6d7ab3b,0x26d72b3b,0xa6d7ab3b,0xaa6daadd,0x2bea23c6,0xa8c4281d,0xa0b2abc3,0x2bea2a6d,0xa0b228c4,0xabeaaa6d,0x20b2a8c4,
  0xab88a9ed,0xab3babfe,0xa564a95f,0x26d71a48,0x3bfb3bff,0x3be53bf2,0x3bbf3bd4,0x3b873ba5,0x3bd03bfb,0x3b013b7c,0x399d3a60,0x378538bc,
  0x35173b52,0xbbc9b7c8,0xb074ba9b,0x3bfe391b,0x319e3b27,0xbbf3b979,0x363cb80a,0x3a2d3bc5,0xba093986,0x3a7eb8f8,0xbae5385f,0x3b3db77a,
  0xbabd393c,0x3bb0b699,0xbc00305b,0x3ba730d7,0xbb2a35c8,0xb8353bb2,0x3a64b1e8,0x3962bbf7,0xba90350b,0xba413bff,0x3602340e,0x3bf6bad8,
  0xac6aa5e4,0xb122af59,0xb402b294,0xb56ab4b7,0xb2deac9c,0xb7bdb5a5,0xb9b3b8d6,0xbb10ba73,0xbb96b676,0xb359bafe,0x3bec3884,0x2a163a29,
  0xbbe0b72c,0x2f27b9d6,0x3b5e3ae8,0xb91633a2,0xb941b9c9,0x38ad3a45,0xb80fbab3,0x36d23b13,0xb850ba0d,0x346f3b4a,0x1fdbbbed,0xb4ab3be8,
  0x3721bb76,0xbace3463,0xb8d13bdd,0x39ebadfb,0x3894bb98,0xb8fd281f,0xbb6a3bbd,0x2e2d3825,0x3b3f3b65,0x3ae83b16,0x3a813ab6,0x3a0d3a49,
  0x3263356a,0xad972b43,0xb5dfb359,0xb8eeb7f3,0xa9b139aa,0xbbedba25,0x3340b889,0x3b983afb,0xbaa2aa16,0xb4cfbb8e,0x3c0038ad,0xb44b38e5,
  0xbb853625,0x3bbdb4c3,0xbbe432ad,0x3bfbaf8b,0xbaacb6d2,0x39243954,0xb65fbace,0x2fbd3bb8,0xb9661648,0xba603bf8,0x383a31cf,0x3b27bbb3,
  0x3219b9eb,0xbb1836f4,0xb9903be5,0x37dd3010,0xb6c6b61a,0xb80ab76f,0xb8a8b85a,0xb93cb8f3,0xbbd7bb87,0xbbf8bbfd,0xbb71bbc9,0xba4dbaf1,
  0xbbfeb9a6,0x305bb91f,0x3bcb3a97,0xb50b37d2,0xb87abbfe,0x3ba13546,0x24523a7e,0xbbb5ba54,0xb576bb63,0x340e3ba3,0xb13bbbd3,0x2c9c3bf2,
  0x386abb3d,0xba2139f8,0x3b57b835,0xbbf13432,0x39e7bc00,0xb8d6adc9,0xbacb3bde,0x372c3457,0x3bdab962,0x3764bb35,0xb9c03122,0xbaf73bef,
  0x398b39cd,0x38fd3946,0x386538b2,0x37853815,0xba85b9c9,0xbb92bb1e,0xbbfebbdd,0xbbc2bbf5,0xb66b3682,0xbb01bb94,0x387fb371,0x3a2d3beb,
  0xbac7bb76,0x3a00ad33,0x36bb3bd4,0xbbeab79b,0xbc0026ad,0x3bf32c38,0xbbd6b109,0x3ba733eb,0x3153bbff,0xb70a3b9e,0x396bba9b,0xbade390c,
  0xb5d4b5bc,0xbbb03b2c,0x32013830,0x3bf6ba67,0x3bccbb52,0x2c06b92e,0xbb83385f,0xb8c73bab,0xb9c5b982,0xba41ba04,0xbab0ba7a,0xbb10bae1,
  0xb8a3b986,0xb52fb74e,0xa94db1e8,0x33d32e91,0xbb54bb4f,0x37bdb523,0x3a9e3bc8,0xb916308d,0x3840b5c8,0x394a3bf9,0xbb42b294,0xb0a6bb0a,
  0x251bbbff,0xaf273bfc,0x327cbbe6,0xb4ab3bc0,0x3be325e4,0xbb2fb4e7,0x39e33884,0xb81aba35,0x3b73bb78,0xb46fb715,0xbbdc3ad1,0x2e2d38cc,
  0x33283676,0x3bfcba19,0x3581bab3,0xba6b3493,0x363136dd,0x34cf3581,0x32c6341a,0x2fbd3153,0xbae1bb65,0xb970ba39,0xb715b889,0xb16cb4f3,
  0xb9a12a7a,0xb924bbfe,0x3a933042,0x37dd3bcc,0x308db9aa,0x3b453b07,0xb94632ad,0xb845bbfa,0xbb68b55e,0x3b1836bb,0xbabab805,0x3a4d38a3,
  0x3bc0b625,0xbbfe2ec3,0x3b9431cf,0xba89b742,0x9cb6b95d,0xbbf8396b,0xb1b63a5c,0x3bb5b840,0x38cc9648,0x3b81bbac,0xac38b85a,0xbbce3933,
  0xbb60bb3a,0xbba1bb83,0xbbd2bbbc,0xbbf1bbe3,0x3815361a,0x39df3907,0x3b2c3a97,0x3be23b9c,0xb9afbbfd,0x3a21294d,0x388e3bee,0xbaf7b328,
  0x3beb39a6,0xb6af37a6,0xba04bbd3,0x3ac42d00,0x360ebb89,0xb7643b42,0x3855baeb,0xb8ee3a85,0x33eb3b63,0x28e8bbf5,0xb5233bde,0x389ebb21,
  0x3c00b9f0,0x2d97b9e3,0xbbdf38db,0xb44b3ac7,0xba673c00,0x358d3487,0x3bfcbab6,0x330fba15,0x3b7a3bf1,0x394a3a93,0x33893764,0xb3d39cb6,
  0x3afb3be2,0x35eb3946,0xb4c328e8,0xbaa9b8cc,0x27763af7,0xbb2fbaba,0x3a76ad97,0x30a63b60,0xaf8b3ac4,0xb994bb94,0x3bf8358d,0xb8743815,
  0xbb4c38ee,0x3bfcb1b6,0xbad5b4cf,0x381a39af,0xbbb3389e,0x3b592c38,0xb76fb970,0xb24b3beb,0xb9d2344b,0xbb923bd2,0xb0f03924,0x3a6bb60e,
  0xb8f3330f,0xbc003b2c,0xb91f3b45,0x323233eb,0xb5b1afbd,0xba00b88e,0xbbc6bb18,0xbbc2bc00,0xb7d2b16c,0xbb6fba04,0xbba3bbfe,0xb86fba67,
  0xbbffb7dd,0x370ab855,0x38b73bf8,0xbbeab631,0xbbf2b845,0x39bcb523,0x2dc93b81,0xbaa5bae1,0xb68dba4d,0xac063bdf,0x382abba1,0xbade39a1,
  0xb457ba89,0xb6543bfc,0x3b16b9df,0xbbd8308d,0x397dbbb5,0xb52fb2c6,0xbbe73a21,0xb8c73b68,0x3a49bbce,0x2311b715,0xba2536af,0xbbd93bc0,
  0xb958b785,0xbb81ba9e,0xbbefbbf3,0xba89bb73,0xbbf7bbc2,0xb9b8bb42,0xaf59b70a,0x384a3328,0xbb8bba2d,0x39dfb27c,0x34263bb0,0xbbceb98b,
  0xb4b7bbea,0x3b6c39e3,0xbafe2c06,0x3185ba85,0xaadebba7,0xb6af3bdc,0x3a58ba41,0xbbe2366b,0x3a29bade,0xbc003581,0x3a45352f,0xb2f7bac7,
  0x3b37bbf6,0x28e8b865,0xbaee37bd,0xbac43c00,0x3b13b8c7,0x3b5cbbfe,0x3463b94a,0xb8993153,0xb9f4bb10,0xb58db87f,0x3029af27,0x389e35d4,
  0x2dfbb3d3,0x399936bb,0x3bf23b2f,0x3ac13bcc,0x3552b916,0x39703bd6,0xbbbab46f,0x330fb9c5,0x3ba530a6,0xb5f7396b,0xb7c8bbfc,0x3be138a3,
  0x3bfdb4ab,0xbb45b201,0x38e038fd,0xb16cbb54,0x391b381a,0xa17fbb83,0xb8f83b92,0x3bcfb840,0x36e82e2d,0x3bfebab0,0x37febb01,0xb845251b,
  0xb77a3a6b,0x3648294d,0x3bb2ba00,0x3a8cbbe3,0xb742b93c,0x2311b340,0x37a6340e,0x3aa93966,0x3b963a4d,0x3b7f3c00,0x380f3a21,0xb0be3219,
  0x3933b50b,0x35eb3be4,0xbbf5b8d6,0x3874b6c6,0x39413bb5,0xbbffb65f,0x38d1b764,0x33ba3bd7,0x3b9c2c9c,0xb994b83a,0x34873ae8,0x324bbbfe,
  0xb7213bf1,0x3b47b990,0xbbbf2d97,0x38c1387a,0x2d00372c,0x3b59b8a8,0x3a39bbed,0xb232b576,0xbbfb3af7,0xb9743b71,0x307434cf,0x3adbb86a,
  0x3b213a0d,0x3c003bcb,0x3b073bbd,0x386f39e7,0x351738ee,0xb599a452,0xbae5b924,0xbbe9bbda,0x3a153b98,0xbb6fb13b,0x2ec3ba60,0x3aa53b3f,
  0xba09344b,0xa884bb57,0x3a643b18,0xbbc3b263,0xb4f33bfb,0x39bcbacb,0xbbac380a,0x3bd8a9b1,0xbb2aafbd,0x36a439c0,0x3402bbf8,0xba6f3aa2,
  0xbbfa3b27,0xb6543a81,0x3907b05b,0x3bd9bb85,0x2c6ab7dd,0xb9da35df,0xbbec3ba1,0xb8203aac,0x3bf53b87,0x3b6c3bec,0x392e3a7e,0x32f73721,
  0xb9e7b785,0xbbfcbb5e,0xba81bbb0,0xb43eb894,0x379b3bfe,0xbc00b80f,0x374eb835,0x38993bfb,0xbb3fba2d,0x3b329fdb,0xb3403a41,0xb8eabbd0,
  0xb90c3b3d,0x3b5cb8d1,0xbbf93122,0x3ac13517,0x29b1bba7,0xb94f3b6a,0x3be4b7bd,0xbaf4b19e,0xbbab3962,0xb9993bbf,0x34e73359,0x3be1ba09,
  0x3b85bbf6,0x353ab99d,0xb83a2f27,0xbbf03abd,0x2e91356a,0xb5f7b074,0xba19b8ad,0xbbcfbb2a,0xb966bb10,0xaba7b63c,0x38a8346f,0x3bb73a90,
  0xbb0aaa16,0xa17fbae5,0x3b1e3ace,0xba8c2c6a,0x36c6b916,0x36ff3c00,0xbbcbb8fd,0x3a50b2de,0xba35b6d2,0x36483a64,0x2d33bbe5,0xb84a3b96,
  0x3bfeb4ab,0xb9fcb602,0x313b3b01,0x37e8bbe0,0x3493b9eb,0xb9b83402,0xbb9e3bc9,0xb1853941,0x35762e2d,0x3b90b9b3,0x3acbbbf3,0x2fefb850,
  0x3a543bcf,0x2884374e,0xb9f8b648,0xbbe9bbab,0x398b3bb7,0xb4db3340,0xbbdcb9fc,0xb911bb85,0xb4323a8c,0xb6a4bbf9,0x3b3539b8,0xbbc3ae91,
  0xb66b3a50,0xad65bbe4,0x38653b90,0xbb0db966,0xbbef384a,0x39da34e7,0x2b43bb6c,0xba6f3b0a,0xbc0037e8,0x3759383a,0x387fbbfc,0xbbf636c6,
  0xb7f33185,0xbb7f3a19,0xbb8e3c00,0xb8203a35,0xb5d42fef,0xba1d38a8,0xbbd63b32,0xbba93bfe,0xb8e5b2f7,0xbbffbb1e,0xb954bb5c,0x30beb493,
  0xb9c5b43e,0xbb9fbbcb,0xb201b94f,0x3a313576,0xbbb8b899,0x3b47ad33,0xb6f43999,0xb3babbf5,0xbb54b8ea,0x3bf9313b,0xbab0353a,0x3790b9e7,
  0xb010bac1,0xb9743b9e,0x3bfdb5f7,0xb8c1b79b,0x251bbaf4,0xbb1b3acb,0x3a9e2ba7,0x2e5fbb3f,0x3af1bbe1,0x3599b92e,0xb546a17f,0xbadb390c,
  0x3b73bbf0,0x3929ba81,0x327cb6ff,0xb49f29b1,0xb825baa9,0x353aaec3,0x3b7c3994,0x3af43bfa,0x360eb0be,0x3bf43a64,0x388e3b47,0xb7372c6a,
  0x38bcb874,0x2ba73bac,0xb979bb59,0x3bf03742,0x3c0033ba,0xbb043402,0x3855b974,0xacce3b96,0x3bc5b24b,0xb6ffb907,0xb6993c00,0x3bb7b933,
  0x363138c1,0x3902bbec,0xbbdf3599,0x34ff3941,0x30d73232,0x39fcb7a6,0x3bffbb6f,0x3a50bb9c,0xb9a13adb,0xb47b380f,0x32c62884,0x3937b721,
  0x3ad8386f,0x3b903bf5,0x35a539bc,0xb7e8ad00,0x3b683be9,0x2ef538d1,0xba93b6a4,0xbb24bbfb,0x3a733aa5,0xbbfcb487,0x39d6b654,0xafef3b21,
  0x1cb63bc3,0xb7b2bbbf,0x3aba39da,0xbbfab517,0xb3a23bd8,0x3b32ba39,0xbb4a2311,0x343e3a15,0xbb603a6f,0x3a3d3074,0x31b6bb7f,0xbb9a3a09,
  0xbbe83bd9,0xb94f3b07,0xa81f35eb,0x38eab4f3,0xb9af3820,0xbbae3ae5,0xbbd23bff,0xba113b2a,0x319e389e,0xb929b426,0xbc00bb45,0xb911bb37,
  0xbbffbac1,0xb805bafe,0x382a217f,0x3bfd3b13,0xbabd330f,0x34dbba58,0x36023bfe,0xbb0db9f4,0xb68dbbe1,0x3a5c3a45,0xbbe7b648,0x3b89adfb,
  0xba90b16c,0x2d653aee,0x39b3bb81,0xbbf63552,0x397dbbcf,0xbbbc3463,0x338939b8,0x39f0bba5,0x32deb845,0xb7593029,0xbb5e39df,0xbba93bfd,
  0x3b7aba8c,0x3beebbf2,0x3a76bb6c,0x36ddb91b,0xbbe0ba89,0xba1dbbba,0x1fdbb6af,0x3a3136e8,0xa776b84a,0x3aeb37c8,0x3ad53c00,0xaa7a377a,
  0xb850bbce,0x3b9f38e0,0xbb6a28e8,0x3790b958,0x3b4cb185,0xb8db38f8,0x30f0bb5c,0x355e3bf7,0x3894bbe2,0xbbf937fe,0x399d358d,0x2e5fbb8b,
  0x39d232f7,0x341abbb2,0xbbc63999,0x395d34b7,0x3bd0bac4,0x3b1bbbef,0x363cb970,0xb49faade,0xb5b13899,0x30422f59,0x38b7b5f7,0x3b3aba29,
  0x3219b3d3,0x3b0438b7,0x3b713bfc,0x34ff397d,0x36e83aa9,0xb8b2adc9,0xbbefbb59,0xb5bcba49,0x3bd730a6,0xb902382a,0xa452bb92,0x39373b7a,
  0xb9583874,0x3371bb16,0x34263c00,0xb982bafb,0x387a381a,0x347bbbe7,0xbb573a00,0x3b242776,0xbb8b324b,0x31093a25,0x3a58bb6f,0xbb4f2f8b,
  0xb86a3a6b,0x2ef53389,0x39c0b70a,0x3bfabb4c,0xaadeb232,0xb83034c3,0xbaee39bc,0xbbff3bb3,0x3bda3bc2,0x37b23a76,0xb5df2c06,0xbb9ab9d2,
  0xbb37b86f,0xba7abbf8,0x3029b654,0x3b7838f3,0x32633bea,0xba3dbad5,0x3c00352f,0xba1135b1,0xb9f4baa5,0x3bc8376f,0xbbba2311,0x39cdb7d2,
  0xbaa23ade,0x3baeb0f0,0xb65fb94a,0xb7373bff,0x3552bbd8,0xbbe6391f,0x38e035eb,0x3682bbf2,0xbaac38c7,0xbbf43bc6,0xb9903b2f,0xacce368d,
  0x3bfdbbd9,0x3ad1bba3,0x37feb994,0x26adb457,0x38a33b9a,0xb8dba452,0xbb83bbae,0x2a7ab86a,0x37423b78,0xbab6b426,0xb907bbe6,0x39aa2ade,
  0xb8403a11,0x341abb57,0x294d3bf4,0xb55ebbda,0xb93339cd,0x3889ba58,0xb7a63ad1,0x3625bb37,0xbbe33737,0x304239c0,0x3b42bb04,0xb95db263,
  0xbb9c3682,0xb2ad3aee,0x3bf5b8b2,0x1648b9f4,0xb3282cce,0xb80535df,0xb9e33902,0xbb3a3aa2,0xad0026ad,0xb1cf3029,0xb4873371,0xb61a3552,
  0xba85b4ff,0xba5cbc00,0x3581b47b,0x3bfd3aac,0xbb21b5bc,0xb85abbba,0x3a393109,0x39a63bfd,0xbac7b937,0x3bbc365f,0xbbfeaef5,0x3b89b219,
  0xba15b982,0x3a9738e0,0xbb07b830,0x3b6336e8,0x3153bb24,0xbbee3990,0x36bb37b2,0x39f0bbd7,0x34f3bb4f,0xbbd337fe,0xaec33a7a,0x3c00b958,
  0x3bccbbfa,0x3aebbb71,0x396bba3d,0x36ddb87a,0x3bfabbff,0x3bdebbef,0x3bacbbc8,0x3b65bb8b,0x3bc03911,0x38303b6a,0xb946ad65,0xbb4fbbd0,
  0x3a353bfd,0xb85f30f0,0xbb1ebbbc,0x35c8b5b1,0x38cc3b0d,0xba7ab99d,0x3b943759,0xbbffb19e,0xb4933b89,0x31e8bbc6,0xad333bee,0xa5e4bbff,
  0xb8153bf6,0x3bc8b63c,0xac38ba1d,0xbb783abd,0xbbf539f0,0x329438b7,0x3b9ebaeb,0xb676b68d,0xbbeb3ba9,0xbbe63c00,0xbb2c3b9f,0xb9cd3a90,
  0xb79b36dd,0xb884382a,0xb92e38db,0xb9c9397d,0x33eb3a31,0xbad1b602,0xba04bbf9,0x3682b2de,0xb90c2a7a,0xbab3bbe7,0x374eb41a,0x3b763b7a,
  0xba673790,0x38b2b9b3,0xb5233b1b,0x26adbbe0,0xbbabb55e,0x3bdd3389,0xbbf9b042,0x3bff2776,0xbae12e5f,0xb3713b5e,0x3bfcb929,0xb5bcb850,
  0xae91b95d,0xbbd43a76,0x34e73805,0x3b52bb4c,0x308db49f,0xb1091fdb,0xb71534db,0xb9823894,0x3b0abb3a,0x3a9bbad5,0x3a19ba5c,0x3986b9d2,
  0x2f8bb7e8,0x3bde3979,0x376f3b32,0xb9aab0d7,0x3bb83b24,0xb1223855,0xbbfdba3d,0xaa16b9a1,0x3bb3afef,0xbab63699,0x391fb94f,0xb6253ad8,
  0x30103bfa,0xb359bbdf,0x35463bae,0xb6d2bb68,0x38f3343e,0x3889bbff,0xbba3353a,0x96483a73,0xbaf13b9a,0x38ad32c6,0x39f8bbf4,0xb9eb9cb6,
  0xb7d238ea,0xb2ad35a5,0x2dc92ba7,0x361ab3a2,0xba543a11,0xbace3a93,0xbb353b04,0xbb873b60,0x3bf23af4,0x31cf39d6,0xbb16b6ff,0xb9a6bbe8,
  0xb4323737,0xbbe5baba,0x2b43b902,0x3bfe39af,0x34573bf0,0xb85abb4a,0x3a2539fc,0xbb63b825,0xbbef2cce,0x3bc9b1b6,0xbb8e347b,0x3b3db60e,
  0xba493bb7,0x3a97a81f,0x34c3bb90,0xbc0038bc,0xb7f3b4ff,0xba7e3bd2,0x39542ef5,0x3962bc00,0xbafb3a50,0xbbd33b7c,0xbbf83bfc,0xbb653bc5,
  0x38e5b937,0x3835b88e,0x36f4b7b2,0x356ab631,0xbb13bbe9,0x31e8b6f4,0x3bf239da,0x36763af1,0x3be83911,0x340e3ab0,0xbb7cb759,0xb72cbb73,
  0x2dfbbbc3,0x32943bfd,0xb7c8bb7f,0x39c93a54,0x38253b0d,0xb8d6ba9e,0x39793a1d,0xba0db98b,0x3ba5ba6f,0xb884b546,0xb8f83bff,0x3b76b432,
  0xb8bc3bf6,0x3ae8b27c,0x3699bb9f,0xbb98366b,0x391bb820,0x3ab3b9f8,0x3bb2bb47,0x3bffbbef,0xbbc53ba9,0xbbed3bdc,0xbbff3bf9,0xbbfb3c00,
  0x377ab0be,0x3bdd3b35,0x2f593974,0xbb52b7f3,0x30d73a31,0xbbbdb865,0xb5a5bb1b,0x3b2735d4,0x3bf733ba,0xbbd42b43,0x3afeb599,0xb98638e5,
  0xbad83790,0x3a60b87f,0xb9d63929,0x393cb9c5,0x34b738c1,0x3a9bbb8e,0xba45a884,0xb5c83bb8,0xba732e5f,0xb80a3bd6,0x3b4ab4db,0x350bbb54,
  0xba293adb,0xb85f3954,0xb46336a4,0x25e43010,0x33a2b49f,0x305bb201,0x281fad65,0xac9c251b,0x3f803f80,0x3f803f80,0x3f803f80,0x3f803f80,
  0x3f803f80,0x3f803f80,0x3f803f80,0x3f803f80,0x3f803f80,0x3f803f80,0x3f803f80,0x3f803f80,0x3f803f80,0x3f803f80,0x3f803f80,0x3f803f80,
  0x3f803f80,0x3f803f80,0x3f803f80,0x3f803f80,0x3f803f80,0x3f803f80,0x3f803f80,0x3f803f80,0x3f803f80,0x3f803f80,0x3f803f80,0x3f803f80,
  0x3f803f80,0x3f803f80,0x3f803f80,0x3f803f80,0x3f803f80,0x3f803f80,0x3f803f80,0x3f803f80,0x3f803f80,0x3f803f80,0x3f803f80,0x3f803f80,
  0x3f803f80,0x3f803f80,0x3f803f80,0x3f803f80,0x3f803f80,0x3f803f80,0x3f803f80,0x3f803f80,0x3f803f80,0x3f803f80,0x3f803f80,0x3f803f80,
  0x3f803f80,0x3f803f80,0x3f803f80,0x3f803f80,0x3f803f80,0x3f803f80,0x3f803f80,0x3f803f80,0x3f803f80,0x3f803f80,0x3f803f80,0x3f803f80,
  0x3f803f80,0x3f803f80,0x3f803f80,0x3f803f80,0x3f803f80,0x3f803f80,0x3f803f80,0x3f803f80,0x3f803f80,0x3f803f80,0x3f803f80,0x3f803f80,
  0x3f803f80,0x3f803f80,0x3f803f80,0x3f803f80,0x3f803f80,0x3f803f80,0x3f803f80,0x3f803f80,0x3f803f80,0x3f803f80,0x3f803f80,0x3f803f80,
  0x3f803f80,0x3f803f80,0x3f803f80,0x3f803f80,0x3f803f80,0x3f803f80,0x3f803f80,0x3f803f80,0x3f803f80,0x3f803f80,0x3f803f80,0x3f803f80,
  0x3f803f80,0x3f803f80,0x3f803f80,0x3f803f80,0x3f803f80,0x3f803f80,0x3f803f80,0x3f803f80,0x3f803f80,0x3f803f80,0x3f803f80,0x3f803f80,
  0x3f803f80,0x3f803f80,0x3f803f80,0x3f803f80,0x3f803f80,0x3f803f80,0x3f803f80,0x3f803f80,0x3f803f80,0x3f803f80,0x3f803f80,0x3f803f80,
  0x3f803f80,0x3f803f80,0x3f803f80,0x3f803f80,0x3f803f80,0x3f803f80,0x3f803f80,0x3f803f80,0x3f803f80,0x3f803f80,0x3f803f80,0x3f803f80,
  0x3f803f80,0x3f803f80,0x3f803f80,0x3f803f80,0x3f803f80,0x3f803f80,0x3f803f80,0x3f803f80,0x3f803f80,0x3f803f80,0x3f803f80,0x3f803f80,
  0x3f803f80,0x3f803f80,0x3f803f80,0x3f803f80,0x3f803f80,0x3f803f80,0x3f803f80,0x3f803f80,0x3f803f80,0x3f803f80,0x3f803f80,0x3f803f80,
  0x3f803f80,0x3f803f80,0x3f803f80,0x3f803f80,0x3f803f80,0x3f803f80,0x3f803f80,0x3f803f80,0x3f803f80,0x3f803f80,0x3f803f80,0x3f803f80,
  0x3f803f80,0x3f803f80,0x3f803f80,0x3f803f80,0x3f803f80,0x3f803f80,0x3f803f80,0x3f803f80,0x3f803f80,0x3f803f80,0x3f803f80,0x3f803f80,
  0x3f803f80,0x3f803f80,0x3f803f80,0x3f803f80,0x3f803f80,0x3f803f80,0x3f803f80,0x3f803f80,0x3f803f80,0x3f803f80,0x3f803f80,0x3f803f80,
  0x3f803f80,0x3f803f80,0x3f803f80,0x3f803f80,0x3f803f80,0x3f803f80,0x3f803f80,0x3f803f80,0x3f803f80,0x3f803f80,0x3f803f80,0x3f803f80,
  0x3f803f80,0x3f803f80,0x3f803f80,0x3f803f80,0x3f803f80,0x3f803f80,0x3f803f80,0x3f803f80,0x3f803f80,0x3f803f80,0x3f803f80,0x3f803f80,
  0x3f803f80,0x3f803f80,0x3f803f80,0x3f803f80,0x3f803f80,0x3f803f80,0x3f803f80,0x3f803f80,0x3f803f80,0x3f803f80,0x3f803f80,0x3f803f80,
  0x3f803f80,0x3f803f80,0x3f803f80,0x3f803f80,0x3f803f80,0x3f803f80,0x3f803f80,0x3f803f80,0x3f803f80,0x3f803f80,0x3f803f80,0x3f803f80,
  0x3f803f80,0x3f803f80,0x3f803f80,0x3f803f80,0x3f803f80,0x3f803f80,0x3f803f80,0x3f803f80,0x3f803f80,0x3f803f80,0x3f803f80,0x3f803f80,
  0x3f803f80,0x3f803f80,0x3f803f80,0x3f803f80,0x3f803f80,0x3f803f80,0x3f803f80,0x3f803f80,0x3f803f80,0x3f803f80,0x3f803f80,0x3f803f80,
  0x3f803f80,0x3f803f80,0x3f803f80,0x3f803f80,0x3f803f80,0x3f803f80,0x3f803f80,0x3f803f80,0x3f803f80,0x3f803f80,0x3f803f80,0x3f803f80,
  0x3f803f80,0x3f803f80,0x3f803f80,0x3f803f80,0x3f803f80,0x3f803f80,0x3f803f80,0x3f803f80,0x3f803f80,0x3f803f80,0x3f803f80,0x3f803f80,
  0x3f803f80,0x3f803f80,0x3f803f80,0x3f803f80,0x3f803f80,0x3f803f80,0x3f803f80,0x3f803f80,0x3f803f80,0x3f803f80,0x3f803f80,0x3f803f80,
  0x3f803f80,0x3f803f80,0x3f803f80,0x3f803f80,0x3f803f80,0x3f803f80,0x3f803f80,0x3f803f80,0x3f803f80,0x3f803f80,0x3f803f80,0x3f803f80,
  0x3f803f80,0x3f803f80,0x3f803f80,0x3f803f80,0x3f803f80,0x3f803f80,0x3f803f80,0x3f803f80,0x3f803f80,0x3f803f80,0x3f803f80,0x3f803f80,
  0x3f803f80,0x3f803f80,0x3f803f80,0x3f803f80,0x3f803f80,0x3f803f80,0x3f803f80,0x3f803f80,0x3f803f80,0x3f803f80,0x3f803f80,0x3f803f80,
  0x3f803f80,0x3f803f80,0x3f803f80,0x3f803f80,0x3f803f80,0x3f803f80,0x3f803f80,0x3f803f80,0x3f803f80,0x3f803f80,0x3f803f80,0x3f803f80,
  0x3f803f80,0x3f803f80,0x3f803f80,0x3f803f80,0x3f803f80,0x3f803f80,0x3f803f80,0x3f803f80,0x3f803f80,0x3f803f80,0x3f803f80,0x3f803f80,
  0x3f803f80,0x3f803f80,0x3f803f80,0x3f803f80,0x3f803f80,0x3f803f80,0x3f803f80,0x3f803f80,0x3f803f80,0x3f803f80,0x3f803f80,0x3f803f80,
  0x3f803f80,0x3f803f80,0x3f803f80,0x3f803f80,0x3f803f80,0x3f803f80,0x3f803f80,0x3f803f80,0x3f803f80,0x3f803f80,0x3f803f80,0x3f803f80,
  0x3f803f80,0x3f803f80,0x3f803f80,0x3f803f80,0x3f803f80,0x3f803f80,0x3f803f80,0x3f803f80,0x3f803f80,0x3f803f80,0x3f803f80,0x3f803f80,
  0x3f803f80,0x3f803f80,0x3f803f80,0x3f803f80,0x3f803f80,0x3f803f80,0x3f803f80,0x3f803f80,0x3f803f80,0x3f803f80,0x3f803f80,0x3f803f80,
  0x3f803f80,0x3f803f80,0x3f803f80,0x3f803f80,0x3f803f80,0x3f803f80,0x3f803f80,0x3f803f80,0x3f803f80,0x3f803f80,0x3f803f80,0x3f803f80,
  0x3f803f80,0x3f803f80,0x3f803f80,0x3f803f80,0x3f803f80,0x3f803f80,0x3f803f80,0x3f803f80,0x3f803f80,0x3f803f80,0x3f803f80,0x3f803f80,
  0x3f803f80,0x3f803f80,0x3f803f80,0x3f803f80,0x3f803f80,0x3f803f80,0x3f803f80,0x3f803f80,0x3f803f80,0x3f803f80,0x3f803f80,0x3f803f80,
  0x3f803f80,0x3f803f80,0x3f803f80,0x3f803f80,0x3f803f80,0x3f803f80,0x3f803f80,0x3f803f80,0x3f803f80,0x3f803f80,0x3f803f80,0x3f803f80,
  0x3f803f80,0x3f803f80,0x3f803f80,0x3f803f80,0x3f803f80,0x3f803f80,0x3f803f80,0x3f803f80,0x3f803f80,0x3f803f80,0x3f803f80,0x3f803f80,
  0x3f803f80,0x3f803f80,0x3f803f80,0x3f803f80,0x3f803f80,0x3f803f80,0x3f803f80,0x3f803f80,0x3f803f80,0x3f803f80,0x3f803f80,0x3f803f80,
  0x3f803f80,0x3f803f80,0x3f803f80,0x3f803f80,0x3f803f80,0x3f803f80,0x3f803f80,0x3f803f80,0x3f803f80,0x3f803f80,0x3f803f80,0x3f803f80,
  0x3f803f80,0x3f803f80,0x3f803f80,0x3f803f80,0x3f803f80,0x3f803f80,0x3f803f80,0x3f803f80,0x3f803f80,0x3f803f80,0x3f803f80,0x3f803f80,
  0x3f803f80,0x3f803f80,0x3f803f80,0x3f803f80,
};

__device__ __align__(128) float    g_part[16][8][2176];
__device__ __align__(128) float    g_kv[16][2176];
constexpr int OBLK = 16 * 1024 + 32;
__device__ __align__(128) uint4    g_o[16 * OBLK];
#define GSTAMP(role, i) do {} while (0)
#define STAMP(role, i) do {} while (0)
#define PDUMP(role) do {} while (0)
#define PROF_SMEM 0

constexpr int STAGE_BYTES = 57344;
constexpr int OFF_H = 4 * 16384, OFF_VP = 9 * 16384, OFF_SPARE = 10 * 16384;
constexpr int OFF_XT = 172032, XT_STRIDE = 4112;
constexpr int OFF_BAR = 204928, OFF_EPOCH = OFF_BAR + 640, OFF_EX = OFF_BAR + 656, OFF_D = OFF_BAR + 672, OFF_SCALE = OFF_BAR + 704;
constexpr int OFF_F2F = 205824, OFF_F2I = 207872, OFF_F4 = 209920, OFF_ONES = 214016, OFF_KVB = 214016;
constexpr int OFF_STG = 219136, STG_STRIDE = 4352, SMEM_TOTAL = 232192 + PROF_SMEM;
enum { B_FULL1 = 0, B_EMPTY1 = 3, B_Q = 6, B_ODONE1 = 7, B_O1RDY = 8, B_H = 9, B_XRAW = 10, B_XT = 11, B_KV = 12, B_Y = 13,  B_AFREE = 15,
       B_STG = 18, B_ODONE = 24, B_XFREE = 25, B_FULL2 = 33, B_CONS2 = 49, B_SFREE = 14, B_KV1 = 61, B_OLOC = 60, B_PKRDY = 62, B_PKFREE = 64, B_H2 = 65, B_G1DONE = 66, B_COUNT = 67, B_FIRST = 67 };
constexpr uint64_t SLOT_A = 0x6859468594685948ull, SLOT_B = 0x7103271032710326ull;
constexpr int NPRE = 6, BEARLY = 3;
__host__ __device__ constexpr int bar_count(int i) {
  return i < B_EMPTY1 ? 1 : i < B_Q ? 4 : i == B_XT ? 4 : i == B_H ? 4 : (i == B_SFREE || i == B_G1DONE) ? 2 : i >= B_PKFREE ? 4 : i >= B_PKRDY ? 8 : i == B_Y ? 9
       : (i >= B_AFREE && i < B_STG) ? 16 : (i == B_ODONE || i == B_ODONE1) ? 8 : (i >= B_XFREE && i < B_FULL2) ? 4
       : i == B_KV1 ? 1 : i == B_OLOC ? 2 : i >= B_CONS2 ? 4 : (i >= B_FULL2 && i < B_FULL2 + NPRE) ? 2 : 1;
}
__host__ __device__ constexpr uint64_t bar_counts(int r) {
  uint64_t v = 0;
  for (int w = 0; w < 11; w++) v |= (uint64_t)(bar_count(1 + 11 * r + w) - 1) << (4 * w);
  return v;
}
constexpr uint32_t SW128 = 64 | (1u << 30);
constexpr int SPIN_LIMIT = 1 << 22;
#define SPLIT0 2
#define OLOC 1
#define G2E 1
#define G2P 1
#define RC 200
#define PFD 3
#define PD1 700
#define PD2 450
#define QPF 6
#define BPACE 250
#define OCH 3
#define O1D 0
#define HOLD2 12
#define D1 100
#define TRICK 3
#define HSTART 1500
#define PACE 800

__device__ __forceinline__ uint32_t smem_u32(const void* p) { return (uint32_t)__cvta_generic_to_shared(p); }
__device__ __forceinline__ void wg_fence() { asm volatile("wgmma.fence.sync.aligned;" ::: "memory"); }
__device__ __forceinline__ void wg_commit() { asm volatile("wgmma.commit_group.sync.aligned;" ::: "memory"); }
template <int N> __device__ __forceinline__ void wg_wait() { asm volatile("wgmma.wait_group.sync.aligned %0;" ::"n"(N) : "memory"); }
template <int N> __device__ __forceinline__ void keep(float (&d)[N]) {
#pragma unroll
  for (int i = 0; i < N; i++) asm volatile("" : "+f"(d[i])::"memory");
}
__device__ __forceinline__ void mbar_init(uint32_t bar, int cnt) { asm volatile("mbarrier.init.shared::cta.b64 [%0], %1;" ::"r"(bar), "r"(cnt)); }
__device__ __forceinline__ void mbar_expect(uint32_t bar, int bytes) { asm volatile("mbarrier.arrive.expect_tx.shared::cta.b64 _, [%0], %1;" ::"r"(bar), "r"(bytes) : "memory"); }
__device__ __forceinline__ void mbar_arrive(uint32_t bar) { asm volatile("mbarrier.arrive.shared::cta.b64 _, [%0];" ::"r"(bar) : "memory"); }
__device__ __forceinline__ void mbar_arrive_cl(uint32_t bar, uint32_t cta) {
  asm volatile("{\n.reg .b32 r;\nmapa.shared::cluster.u32 r, %0, %1;\nmbarrier.arrive.shared::cluster.b64 _, [r];\n}\n" ::"r"(bar), "r"(cta) : "memory");
}
__device__ __forceinline__ void mbar_wait(uint32_t bar, uint32_t parity) {
  asm volatile("{\n.reg .pred p;\n.reg .u32 n;\nmov.u32 n, 0;\n"
               "W_%=:\nmbarrier.try_wait.parity.shared::cta.b64 p, [%0], %1;\n@p bra D_%=;\n"
               "add.u32 n, n, 1;\nsetp.lt.u32 p, n, %2;\n@p bra W_%=;\ntrap;\nD_%=:\n}\n" ::"r"(bar), "r"(parity), "n"(SPIN_LIMIT) : "memory");
}
__device__ __forceinline__ void fence_async() { asm volatile("fence.proxy.async.shared::cta;" ::: "memory"); }
__device__ __forceinline__ void bar_sync(int id) { asm volatile("bar.sync %0, 128;" ::"r"(id) : "memory"); }
__device__ __forceinline__ void tma2d(uint32_t dst, const CUtensorMap* m, int c0, int c1, uint32_t bar) {
  asm volatile("cp.async.bulk.tensor.2d.shared::cluster.global.mbarrier::complete_tx::bytes [%0], [%1, {%3, %4}], [%2];"
               ::"r"(dst), "l"(m), "r"(bar), "r"(c0), "r"(c1) : "memory");
}
__device__ __forceinline__ void tma2d_mc(uint32_t dst, const CUtensorMap* m, int c0, int c1, uint32_t bar) {
  asm volatile("cp.async.bulk.tensor.2d.shared::cluster.global.mbarrier::complete_tx::bytes.multicast::cluster [%0], [%1, {%3, %4}], [%2], %5;"
               ::"r"(dst), "l"(m), "r"(bar), "r"(c0), "r"(c1), "h"((uint16_t)3) : "memory");
}
__device__ __forceinline__ void tma3d(uint32_t dst, const CUtensorMap* m, int c0, int c1, int c2, uint32_t bar) {
  asm volatile("cp.async.bulk.tensor.3d.shared::cluster.global.mbarrier::complete_tx::bytes [%0], [%1, {%3, %4, %5}], [%2];"
               ::"r"(dst), "l"(m), "r"(bar), "r"(c0), "r"(c1), "r"(c2) : "memory");
}
__device__ __forceinline__ void tma4d(uint32_t dst, const CUtensorMap* m, int c0, int c1, int c2, int c3, uint32_t bar) {
  asm volatile("cp.async.bulk.tensor.4d.shared::cluster.global.mbarrier::complete_tx::bytes [%0], [%1, {%3, %4, %5, %6}], [%2];"
               ::"r"(dst), "l"(m), "r"(bar), "r"(c0), "r"(c1), "r"(c2), "r"(c3) : "memory");
}
__device__ __forceinline__ void bulk_ld(uint32_t dst, const void* src, int bytes, uint32_t bar) {
  asm volatile("cp.async.bulk.shared::cluster.global.mbarrier::complete_tx::bytes [%0], [%1], %2, [%3];" ::"r"(dst), "l"(src), "r"(bytes), "r"(bar) : "memory");
}
__device__ __forceinline__ void bulk_ld_mc(uint32_t dst, const void* src, int bytes, uint32_t bar) {
  asm volatile("cp.async.bulk.shared::cluster.global.mbarrier::complete_tx::bytes.multicast::cluster [%0], [%1], %2, [%3], %4;"
               ::"r"(dst), "l"(src), "r"(bytes), "r"(bar), "h"((uint16_t)3) : "memory");
}
__device__ __forceinline__ void tma2d_st(const CUtensorMap* m, uint32_t src, int c0, int c1) {
  asm volatile("cp.async.bulk.tensor.2d.global.shared::cta.bulk_group [%0, {%2, %3}], [%1];" ::"l"(m), "r"(src), "r"(c0), "r"(c1) : "memory");
}
__device__ __forceinline__ void ldsm4(uint32_t (&r)[4], uint32_t a) {
  asm volatile("ldmatrix.sync.aligned.m8n8.x4.shared.b16 {%0,%1,%2,%3}, [%4];" : "=r"(r[0]), "=r"(r[1]), "=r"(r[2]), "=r"(r[3]) : "r"(a) : "memory");
}
__device__ __forceinline__ void ldsm4t(uint32_t (&r)[4], uint32_t a) {
  asm volatile("ldmatrix.sync.aligned.m8n8.x4.trans.shared.b16 {%0,%1,%2,%3}, [%4];" : "=r"(r[0]), "=r"(r[1]), "=r"(r[2]), "=r"(r[3]) : "r"(a) : "memory");
}
__device__ __forceinline__ void stsm4(uint32_t a, uint32_t r0, uint32_t r1, uint32_t r2, uint32_t r3) {
  asm volatile("stmatrix.sync.aligned.m8n8.x4.shared.b16 [%0], {%1,%2,%3,%4};" ::"r"(a), "r"(r0), "r"(r1), "r"(r2), "r"(r3) : "memory");
}
__device__ __forceinline__ uint32_t pk2(float lo, float hi) { uint32_t r; asm("cvt.rn.bf16x2.f32 %0, %1, %2;" : "=r"(r) : "f"(hi), "f"(lo)); return r; }
__device__ __forceinline__ uint32_t hmul(uint32_t a, uint32_t b) { uint32_t r; asm("mul.rn.bf16x2 %0, %1, %2;" : "=r"(r) : "r"(a), "r"(b)); return r; }
__device__ __forceinline__ uint32_t hadd(uint32_t a, uint32_t b) { uint32_t r; asm("add.rn.bf16x2 %0, %1, %2;" : "=r"(r) : "r"(a), "r"(b)); return r; }
__device__ __forceinline__ uint32_t hmin(uint32_t a, uint32_t b) { uint32_t r; asm("min.bf16x2 %0, %1, %2;" : "=r"(r) : "r"(a), "r"(b)); return r; }
__device__ __forceinline__ uint32_t hmaxabs(uint32_t a, uint32_t b) { uint32_t r; asm("max.xorsign.abs.bf16x2 %0, %1, %2;" : "=r"(r) : "r"(a), "r"(b)); return r; }
__device__ __forceinline__ float ex2(float x) { float r; asm("ex2.approx.ftz.f32 %0, %1;" : "=f"(r) : "f"(x)); return r; }
__device__ __forceinline__ float rcp_fast(float x) { float r; asm("rcp.approx.ftz.f32 %0, %1;" : "=f"(r) : "f"(x)); return r; }
__device__ __forceinline__ uint32_t phi2(float lo, float hi) {
  uint32_t t;
  asm("cvt.rn.relu.bf16x2.f32 %0, %1, %2;" : "=r"(t) : "f"(hi), "f"(lo));
  const uint32_t e = pk2(ex2(lo * 1.4426950408889634f), ex2(hi * 1.4426950408889634f));
  return hadd(hadd(t, hmin(e, 0x3F803F80u)), 0x35863586u);
}
__device__ __forceinline__ bool opaque_true() { uint32_t v; asm volatile("mov.u32 %0, %%nctaid.y;" : "=r"(v)); return v != 0; }
__device__ __forceinline__ int norm_exp(uint32_t (&v)[32], float f0) {
  uint32_t m[4] = {hmaxabs(__float_as_uint(f0) >> 16, v[0]), v[1], v[2], v[3]};
#pragma unroll
  for (int i = 4; i < 32; i++) m[i & 3] = hmaxabs(m[i & 3], v[i]);
  m[0] = hmaxabs(hmaxabs(m[0], m[1]), hmaxabs(m[2], m[3]));
  const int e = min(max((int)(__reduce_max_sync(~0u, max(m[0] & 0x7FFFu, (m[0] >> 16) & 0x7FFFu)) >> 7), 1), 253);
  if (e > 141) {
#pragma unroll
    for (int i = 0; i < 32; i++) v[i] = hmul(v[i], 0x07000700u);
  }
  return e;
}
__device__ __forceinline__ void norm_cvt(uint32_t (&v)[32], float f0, int e) {
  const uint32_t sc = (e > 141 ? 255 - e : 142 - e) * 0x00800080u;
#pragma unroll
  for (int i = 0; i < 32; i++) {
    const uint32_t a = hmul(v[i], sc);
    v[i] = (a & 0x0FFF0FFFu) * 7 + a;
  }
  v[0] = __byte_perm(v[0], __half_as_ushort(__float2half_rn(f0 * __uint_as_float((254 - e) << 23))), 0x3254);
}
__device__ __forceinline__ void poll_ge(const unsigned* p, unsigned target) {
#pragma unroll 1
  for (int n = 0; n < SPIN_LIMIT; n++) {
    unsigned v;
    asm volatile("ld.relaxed.gpu.global.u32 %0, [%1];" : "=r"(v) : "l"(p) : "memory");
    if (__all_sync(~0u, (int)(v - target) >= 0)) { asm volatile("fence.acquire.gpu;" ::: "memory"); return; }
  }
  __trap();
}

__device__ __forceinline__ bool elect_one() {
  uint32_t p;
  asm volatile("{\n.reg .pred p;\nelect.sync _|p, 0xffffffff;\nselp.u32 %0, 1, 0, p;\n}\n" : "=r"(p));
  return p;
}
__device__ __forceinline__ uint4 ld_na4(const void* p) {
  uint4 v;
  asm volatile("ld.global.L1::no_allocate.v4.u32 {%0,%1,%2,%3}, [%4];" : "=r"(v.x), "=r"(v.y), "=r"(v.z), "=r"(v.w) : "l"(p) : "memory");
  return v;
}
__device__ __forceinline__ void st_cg4(void* p, uint4 v) {
  asm volatile("st.global.cg.v4.u32 [%0], {%1,%2,%3,%4};" ::"l"(p), "r"(v.x), "r"(v.y), "r"(v.z), "r"(v.w) : "memory");
}
__device__ __forceinline__ uint32_t mapa(uint32_t a, uint32_t cta) { uint32_t r; asm("mapa.shared::cluster.u32 %0, %1, %2;" : "=r"(r) : "r"(a), "r"(cta)); return r; }
__device__ __forceinline__ void st_async(uint32_t a, uint32_t v, uint32_t bar) {
  asm volatile("st.async.weak.shared::cluster.mbarrier::complete_tx::bytes.b32 [%0], %1, [%2];" ::"r"(a), "r"(v), "r"(bar) : "memory");
}
__device__ __forceinline__ void st_async4(uint32_t a, uint32_t x, uint32_t y, uint32_t z, uint32_t w, uint32_t bar) {
  asm volatile("st.async.weak.shared::cluster.mbarrier::complete_tx::bytes.v4.b32 [%0], {%1,%2,%3,%4}, [%5];" ::"r"(a), "r"(x), "r"(y), "r"(z), "r"(w), "r"(bar) : "memory");
}
__device__ __forceinline__ void tma3d_st(const CUtensorMap* m, uint32_t src, int c0, int c1, int c2) {
  asm volatile("cp.async.bulk.tensor.3d.global.shared::cta.bulk_group [%0, {%2, %3, %4}], [%1];" ::"l"(m), "r"(src), "r"(c0), "r"(c1), "r"(c2) : "memory");
}
__device__ __forceinline__ uint4 ld_rlx4(const void* p) {
  uint4 v;
  asm volatile("{\n.reg .b128 t;\n.reg .b64 a, b;\nld.relaxed.gpu.global.b128 t, [%4];\nmov.b128 {a, b}, t;\nmov.b64 {%0, %1}, a;\nmov.b64 {%2, %3}, b;\n}\n"
               : "=r"(v.x), "=r"(v.y), "=r"(v.z), "=r"(v.w) : "l"(p) : "memory");
  return v;
}
__device__ __forceinline__ void ld_stale4(uint4& v, const void* p, uint32_t tag) {
  asm volatile("{\n.reg .b128 t;\n.reg .b64 a, b;\n.reg .b32 x;\n.reg .pred p;\n"
               "lop3.b32 x, %0, %5, 1, 0x28;\nsetp.ne.u32 p, x, 0;\n"
               "mov.b64 a, {%0, %1};\nmov.b64 b, {%2, %3};\nmov.b128 t, {a, b};\n"
               "@p ld.relaxed.gpu.global.b128 t, [%4];\n"
               "mov.b128 {a, b}, t;\nmov.b64 {%0, %1}, a;\nmov.b64 {%2, %3}, b;\n}\n"
               : "+r"(v.x), "+r"(v.y), "+r"(v.z), "+r"(v.w) : "l"(p), "r"(tag) : "memory");
}
__device__ __forceinline__ void st_tag4(void* p, float a, float b, float c, float d, uint32_t tag) {
  asm volatile("{\n.reg .b128 t;\n.reg .b64 a, b;\nmov.b64 a, {%1, %2};\nmov.b64 b, {%3, %4};\nmov.b128 t, {a, b};\nst.relaxed.gpu.global.b128 [%0], t;\n}\n"
               ::"l"(p), "r"((__float_as_uint(a) & ~1u) | tag), "f"(b), "f"(c), "f"(d) : "memory");
}
__device__ __forceinline__ uint32_t stale8(const uint4 (&f)[8], uint32_t tag) {
  uint32_t r[4];
#pragma unroll
  for (int i = 0; i < 4; i++) asm("lop3.b32 %0, %1, %2, %3, 0x7E;" : "=r"(r[i]) : "r"(f[2 * i].x), "r"(f[2 * i + 1].x), "r"(tag));
  asm("lop3.b32 %0, %0, %1, %2, 0xFE;" : "+r"(r[0]) : "r"(r[1]), "r"(r[2]));
  return r[0] | r[3];
}

struct ConvC { uint32_t a1[2][4], wa[2], wb[2], sg; };
__device__ __forceinline__ uint64_t dsc(uint32_t lo, uint32_t hi) { return ((uint64_t)hi << 32) | lo; }
__device__ __forceinline__ uint32_t hfma(uint32_t a, uint32_t b, uint32_t c) { uint32_t r; asm("fma.rn.f16x2 %0, %1, %2, %3;" : "=r"(r) : "r"(a), "r"(b), "r"(c)); return r; }
__device__ __forceinline__ uint32_t hfnma(uint32_t a, uint32_t b, uint32_t c) { uint32_t r; asm("{.reg .b32 n; neg.f16x2 n, %1; fma.rn.f16x2 %0, n, %2, %3;}" : "=r"(r) : "r"(a), "r"(b), "r"(c)); return r; }
__device__ __forceinline__ uint32_t hmul16(uint32_t a, uint32_t b) { uint32_t r; asm("mul.rn.f16x2 %0, %1, %2;" : "=r"(r) : "r"(a), "r"(b)); return r; }
template <int N> __device__ __forceinline__ void keepu(uint32_t (&d)[N]) {
#pragma unroll
  for (int i = 0; i < N; i++) asm volatile("" : "+r"(d[i])::"memory");
}
__device__ __forceinline__ void conv_m1(const ConvC& K, uint32_t (&u)[16], uint32_t l) {
  wg_fence();
  wgmma_hrs_n64<1>(u, K.a1[0][0], K.a1[0][1], K.a1[0][2], K.a1[0][3], dsc(l, 32), 0);
  wgmma_hrs_n64<1>(u, K.a1[1][0], K.a1[1][1], K.a1[1][2], K.a1[1][3], dsc(l + 16, 32), 1);
  wg_commit();
}
__device__ __forceinline__ void conv_s2(const ConvC& K, uint32_t (&u)[16], uint32_t (&Z)[2][8], uint32_t dfl) {
  uint32_t fr[8], fi[8];
#pragma unroll
  for (int c = 0; c < 8; c++) {
    const uint32_t r = hfma(K.wa[c & 1], u[2 * c + 1], u[2 * c]);
    fi[c] = hfma(K.wb[c & 1], r, u[2 * c + 1]);
    fr[c] = hfma(K.wa[c & 1], fi[c], r);
  }
  wg_fence();
#pragma unroll
  for (int p = 0; p < 2; p++) {
    wgmma_hrs_n32<0>(Z[p], fr[4 * p], fr[4 * p + 2], fr[4 * p + 1], fr[4 * p + 3], dsc(dfl, 32), 0);
    wgmma_hrs_n32<0>(Z[p], fi[4 * p], fi[4 * p + 2], fi[4 * p + 1], fi[4 * p + 3], dsc(dfl + 16, 32), 1);
  }
  wg_commit();
}
__device__ __forceinline__ void conv_win(const ConvC& K, const uint32_t (&X)[2][8], uint32_t (&W)[2][8]) {
#pragma unroll
  for (int b = 0; b < 4; b++)
#pragma unroll
    for (int c = 0; c < 2; c++) {
      const uint32_t xr = X[b >> 1][2 * c + (b & 1)], xi = X[b >> 1][4 + 2 * c + (b & 1)];
      const int a = b ? b - 1 : 0;
      W[b >> 1][2 * c + (b & 1)] = b ? hfnma(K.sg, X[a >> 1][4 + 2 * c + (a & 1)], xr) : hmul16(xr, 0x3C003C00u);
      W[b >> 1][4 + 2 * c + (b & 1)] = b ? hfma(K.sg, X[a >> 1][2 * c + (a & 1)], xi) : hmul16(xi, 0x3C003C00u);
    }
}
template <int p>
__device__ __forceinline__ void conv_pw(uint32_t (&X)[2][8], uint32_t (&H)[2][8], uint32_t (&V)[8], uint32_t dil) {
  uint32_t pr[2][2], pi[2][2];
#pragma unroll
  for (int jj = 0; jj < 2; jj++)
#pragma unroll
    for (int c = 0; c < 2; c++) {
      const int j = 2 * p + jj;
      uint32_t sr = 0, si = 0;
#pragma unroll
      for (int a = 0; a <= j; a++) {
        const int b = j - a;
        const uint32_t hr = H[a >> 1][2 * c + (a & 1)], hi = H[a >> 1][4 + 2 * c + (a & 1)];
        const uint32_t xr = X[b >> 1][2 * c + (b & 1)], xi = X[b >> 1][4 + 2 * c + (b & 1)];
        sr = a == 0 ? hmul16(hr, xr) : hfma(hr, xr, sr);
        si = a == 0 ? hmul16(hr, xi) : hfma(hr, xi, si);
        sr = hfnma(hi, xi, sr);
        si = hfma(hi, xr, si);
      }
      pr[jj][c] = sr; pi[jj][c] = si;
    }
  wg_fence();
  wgmma_hrs_n32<0>(V, pr[0][0], pr[1][0], pr[0][1], pr[1][1], dsc(dil, 32), 0);
  wgmma_hrs_n32<0>(V, pi[0][0], pi[1][0], pi[0][1], pi[1][1], dsc(dil + 16, 32), 1);
  wg_commit();
}
template <int p>
__device__ __forceinline__ void conv_it(const ConvC& K, uint32_t (&V)[8], uint32_t vst) {
#pragma unroll
  for (int jj = 0; jj < 2; jj++) {
    uint32_t wr[2], wi[2];
#pragma unroll
    for (int c = 0; c < 2; c++) {
      const uint32_t r = hfnma(K.wa[c], V[4 + 2 * c + jj], V[2 * c + jj]);
      wi[c] = hfnma(K.wb[c], r, V[4 + 2 * c + jj]);
      wr[c] = hfnma(K.wa[c], wi[c], r);
    }
    stsm4(vst + (2 * p + jj) * 2048, wr[0], wr[1], wi[0], wi[1]);
  }
}
__device__ __forceinline__ void conv_m4(uint32_t (&y)[8], uint32_t (&a)[4][4], uint32_t d4l) {
  wg_fence();
  wgmma_hrs_n32<0>(y, a[0][0], a[0][1], a[0][2], a[0][3], dsc(d4l, 64), 0);
#pragma unroll
  for (int s = 1; s < 4; s++) wgmma_hrs_n32<0>(y, a[s][0], a[s][1], a[s][2], a[s][3], dsc(d4l + s * 16, 64), 1);
  wg_commit();
}

struct Params {
  CUtensorMap tmX0, tmW, tmX, tmWo, tmWo1, tmK, tmV, tmQ, tmOA, tmOB;
  const __nv_bfloat16 *shift_k, *h, *D, *x, *w, *wo, *q;
  float *part, *kv;
  uint4* o;
  const uint32_t *thr, *img;
};

__global__ void __cluster_dims__(2, 1, 1) __launch_bounds__(384, 1) fused_kernel(const __grid_constant__ Params P) {
  extern __shared__ __align__(1024) uint8_t smem[];
  const uint32_t sb = __shfl_sync(~0u, smem_u32(smem), 0);
  const uint32_t bars = sb + OFF_BAR;
  const int tid = threadIdx.x, lane = tid & 31;
  const int warp = __shfl_sync(~0u, tid >> 5, 0);
  const int rank = blockIdx.x & 1, cl = blockIdx.x >> 1;
  const unsigned c7 = cl + 6, g7 = (c7 * 37) >> 8;
  const int mb = cl < 4 ? 4 + cl : cl < 36 ? (cl - 4) >> 3 : g7 - 2;
  const int hq = cl < 4 ? 0 : cl < 36 ? (cl - 4) & 7 : 1 + c7 - 7 * g7;
  const int hp = 2 * hq + rank;
  const int rb = 2 * mb + (hq >> 2), cb = hq & 3;
#define BAR(i) (bars + 8 * (i))
#define OCNT(rb, hh) ((unsigned*)(P.o + (rb) * OBLK + 16 * 1024 + 8 * (hh)))
#define EPOCH (OCNT(rb, 2)[hp & 7])

  if (tid == 0) { STAMP(0, 0); GSTAMP(0, 30); }
  if (warp == 8) {
    if (elect_one()) {
      mbar_init(BAR(B_FULL1), 1);
      mbar_init(BAR(B_FIRST), 1);
      asm volatile("fence.mbarrier_init.release.cluster;" ::: "memory");
      mbar_expect(BAR(B_FIRST), STAGE_BYTES - 16384);
      tma2d(sb, &P.tmX0, 0, mb * 256, BAR(B_FIRST));
      tma2d(sb + 16384, &P.tmX0, 0, mb * 256 + 128, BAR(B_FIRST));
      tma3d(sb + 32768, &P.tmW, hp * 64, 0, 0, BAR(B_FIRST));
    }
    if (lane == 0) STAMP(3, 21);
  } else if (lane == 0) {
    const int wi = warp - (warp > 8);
#pragma unroll
    for (int r = 0; r < 6; r++)
      if (r < 5 || wi < B_COUNT - 56) mbar_init(BAR(1 + 11 * r + wi), ((uint32_t)(bar_counts(r) >> (4 * wi)) & 15) + 1);
    asm volatile("fence.mbarrier_init.release.cluster;" ::: "memory");
  }
  if (tid == 0) STAMP(2, 6);
  asm volatile("barrier.cluster.arrive.relaxed.aligned;\nbarrier.cluster.wait.aligned;" ::: "memory");
  if (warp == 8 && elect_one()) {
    mbar_expect(BAR(B_FULL1), 16384);
    tma2d_mc(sb + 8192 + rank * 16384, &P.tmX0, 0, mb * 256 + 64 + rank * 128, BAR(B_FULL1));
  }
  if (tid == 256) STAMP(2, 7);

  if (warp < 8) {
    asm volatile("setmaxnreg.inc.sync.aligned.u32 224;");
    const int wg = warp >> 2, w = warp & 3, g = lane >> 2, q = lane & 3, t = tid & 127;
    const bool elect = (t == 0);
    const uint32_t s16 = (sb & 0x3FFFF) >> 4;
    uint32_t pq[2][16], ux[16], uh[16], X[4][2][8], H[4][2][8];
    ConvC K;
    const uint32_t dfl = s16 + (OFF_F2F >> 4) + (8 << 16), dil = s16 + (OFF_F2I >> 4) + (8 << 16), d4l = s16 + (OFF_F4 >> 4) + (8 << 16);
    const uint32_t xl = s16 + (OFF_XT >> 4) + 4 * wg * (XT_STRIDE >> 4) + (8 << 16);
    const uint32_t hl = s16 + (OFF_H >> 4) + wg * 512 + (8 << 16);
    {
      float acc[2][96];
      if (SPLIT0) {
#pragma unroll
        for (int mt = 0; mt < 2; mt++) {
          mbar_wait(BAR(mt ? B_FULL1 : B_FIRST), 0);
          if (mt == 0 && elect) { STAMP(wg, 1); GSTAMP(wg, 26); }
          wg_fence();
#pragma unroll
          for (int ks = 0; ks < 4; ks++)
            wgmma_ss_n192<0, 1>(acc[mt], dsc(s16 + wg * 1024 + mt * 512 + (1 << 16) + ks * 2, SW128), dsc(s16 + 2048 + (512 << 16) + ks * 128, SW128), ks != 0);
        }
        wg_commit();
      }
      int st = SPLIT0 ? 1 : 0, ph = 0;
#pragma unroll 1
      for (int kb = SPLIT0 ? 1 : 0; kb < 14; kb++) {
        mbar_wait(BAR(B_FULL1 + st), ph);
        if (kb == 0 && elect) { STAMP(wg, 1); GSTAMP(wg, 26); }
        if (kb == 8 && elect) { STAMP(wg, 16); GSTAMP(wg, 25); }
        const uint32_t da = s16 + st * (STAGE_BYTES >> 4) + wg * 1024 + (1 << 16);
        const uint32_t db = s16 + st * (STAGE_BYTES >> 4) + 2048 + (512 << 16);
        wg_fence();
#pragma unroll
        for (int ks = 0; ks < 4; ks++) {
          wgmma_ss_n192<0, 1>(acc[0], dsc(da + ks * 2, SW128), dsc(db + ks * 128, SW128), (kb | ks) != 0);
          wgmma_ss_n192<0, 1>(acc[1], dsc(da + 512 + ks * 2, SW128), dsc(db + ks * 128, SW128), (kb | ks) != 0);
        }
        wg_commit();
        wg_wait<1>();
        if (kb > 0 && t < 2) mbar_arrive_cl(BAR(B_EMPTY1 + (st == 0 ? 2 : st - 1)), t);
        if (++st == 3) { st = 0; ph ^= 1; }
      }
#define TAIL_MMA(mt, stage) do { wg_fence(); _Pragma("unroll") for (int ks = 0; ks < 4; ks++) \
        wgmma_ss_n192<0, 1>(acc[mt], dsc(s16 + (stage) * (STAGE_BYTES >> 4) + wg * 1024 + (mt) * 512 + (1 << 16) + ks * 2, SW128), \
                            dsc(s16 + (stage) * (STAGE_BYTES >> 4) + 2048 + (512 << 16) + ks * 128, SW128), 1); wg_commit(); } while (0)
      mbar_wait(BAR(B_FULL1 + 2), 0);
      TAIL_MMA(0, 2);
      wg_wait<1>();
      if (elect) mbar_arrive(BAR(B_SFREE));
      mbar_wait(BAR(B_FULL1 + 0), 1);
      TAIL_MMA(0, 0);
      TAIL_MMA(1, 2);
      const uint32_t lrow = sb + wg * 16384 + (16 * w + 8 * ((lane >> 3) & 1) + (lane & 7)) * 128 + (((lane >> 4) ^ (lane & 7)) << 4);
#define E1K(mt, i) do { if (opaque_true()) { _Pragma("unroll") for (int j = (i); j < (i) + 2; j++) { \
          const float* a = &acc[mt][32 + 8 * j]; const float* b = a + 32; const uint32_t o = (lrow ^ (j * 32)) + (mt) * 8192; \
          stsm4(o + 2 * STAGE_BYTES, pk2(b[0], b[1]), pk2(b[2], b[3]), pk2(b[4], b[5]), pk2(b[6], b[7])); \
          stsm4(o, phi2(a[0], a[1]), phi2(a[2], a[3]), phi2(a[4], a[5]), phi2(a[6], a[7])); } } } while (0)
#define E1Q(mt) do { if (opaque_true()) { _Pragma("unroll") for (int i = 0; i < 16; i++) pq[mt][i] = phi2(acc[mt][2 * i], acc[mt][2 * i + 1]); } } while (0)
#define LOAD_K() do { const uint4* ct = (const uint4*)P.thr + t; \
        _Pragma("unroll") for (int s = 0; s < 2; s++) { const uint4 u = ld_na4(ct + s * 128); K.a1[s][0] = u.x; K.a1[s][1] = u.y; K.a1[s][2] = u.z; K.a1[s][3] = u.w; } \
        const uint4 u = ld_na4(ct + 2 * 128); K.wa[0] = u.x; K.wa[1] = u.y; K.wb[0] = u.z; K.wb[1] = u.w; \
        K.sg = (lane & 4) ? 0xBC00BC00u : 0x3C003C00u; } while (0)
#define PK_READY(mt) do { fence_async(); __syncwarp(); if (lane == 0) mbar_arrive(BAR(B_PKRDY + (mt))); } while (0)
      wg_wait<1>();
      keep(acc[0]);
      if (elect) STAMP(wg, 18);
      E1K(0, 0);
      TAIL_MMA(1, 0);
      E1K(0, 2);
      if (elect) STAMP(wg, 19);
      PK_READY(0);
      wg_wait<0>();
      keep(acc[1]);
      if (elect) mbar_arrive(BAR(B_G1DONE));
      asm volatile("setmaxnreg.dec.sync.aligned.u32 %0;" ::"n"(RC));
      if (elect) { STAMP(wg, 2); GSTAMP(wg, 27); }
      E1K(1, 0);
      if (elect) STAMP(wg, 20);
      E1K(1, 2);
      if (elect) STAMP(wg, 21);
      PK_READY(1);
      if (elect) STAMP(wg, 3);
      LOAD_K();
      if (elect) STAMP(wg, 4);
      E1Q(0);
      E1Q(1);
      if (elect) STAMP(wg, 17);
      mbar_wait(BAR(B_H), 0);
      conv_m1(K, ux, xl);
      conv_m1(K, uh, hl);
      wg_wait<1>(); keepu(ux);
      if (lane == 0) mbar_arrive_cl(BAR(B_XFREE + 4 * wg), rank ^ 1);
      conv_s2(K, ux, X[0], dfl);
      wg_wait<1>(); keepu(uh);
      conv_s2(K, uh, H[0], dfl);
    }
    if (elect) STAMP(wg, 5);
    float acc[64];
#define G2_MMA(da, db, first) do { wg_fence(); _Pragma("unroll") for (int ks = 0; ks < 4; ks++) \
        wgmma_ss_n128<0, 1>(acc, dsc((da) + ks * 2, SW128), dsc((db) + ks * 128, SW128), ks || !(first)); wg_commit(); } while (0)
    const uint32_t a0 = s16 + wg * 512 + (1 << 16), b0 = s16 + (512 << 16);
    uint32_t cons = mapa(BAR(B_CONS2 - 1 + G2E), t & 1);
    const bool rel = __shfl_sync(~0u, t, lane) < 2;
    {
      uint32_t vst = sb + wg * 8192 + w * 512 + lane * 16, vld = sb + wg * 8192 + w * 2048 + lane * 16;
      uint32_t ya = mapa(sb + OFF_XT + 4 * wg * XT_STRIDE + (2 * rank + (w & 1)) * 1024 + lane * 16, w >> 1);
      const uint32_t ybar = mapa(BAR(B_Y), w >> 1);
      asm volatile("" : "+r"(vst), "+r"(vld), "+r"(ya));
      uint32_t W[2][8], V0[8], V1[8], y[8], a[4][4];
      uint4 ov[4];
      uint4* const ot = P.o + (2 * mb + wg) * OBLK + hq * 1024 + (16 * w + g) * 8 + ((4 * rank + q) ^ g);
#define YOUT(i) do { if ((w >> 1) == rank) { \
          asm volatile("st.shared.v4.b32 [%0], {%1,%2,%3,%4};" ::"r"(ya + (i) * XT_STRIDE), "r"(y[0]), "r"(y[2]), "r"(y[4]), "r"(y[6]) : "memory"); \
          asm volatile("st.shared.v4.b32 [%0], {%1,%2,%3,%4};" ::"r"(ya + (i) * XT_STRIDE + 512), "r"(y[1]), "r"(y[3]), "r"(y[5]), "r"(y[7]) : "memory"); \
        } else { \
          mbar_wait(BAR(B_XFREE + 4 * wg + (i)), 0); \
          st_async4(ya + (i) * XT_STRIDE, y[0], y[2], y[4], y[6], ybar); \
          st_async4(ya + (i) * XT_STRIDE + 512, y[1], y[3], y[5], y[7], ybar); } } while (0)
      auto ocalc = [&](const int hh) {
        if (hh == 0) {
          if (elect) STAMP(wg, 8);
          mbar_wait(BAR(B_KV), 0);
          if (elect) STAMP(wg, 9);
        } else mbar_wait(BAR(B_KV1), 0);
        float oa[2][20];
        wg_fence();
#pragma unroll
        for (int m = 0; m < 4; m++) {
          const uint32_t* p = &pq[m & 1][8 * hh + 4 * (m >> 1)];
          wgmma_rs_n40<1>(oa[m & 1], p[0], p[1], p[2], p[3], dsc(s16 + (OFF_KVB >> 4) + hh * 160 + (m >> 1) * 16 + (8 << 16), 32), m >> 1);
        }
        wg_commit();
        wg_wait<0>();
#pragma unroll
        for (int mt = 0; mt < 2; mt++) {
          float (&o)[20] = oa[mt];
          keep(o);
          const uint32_t den = hadd(pk2(o[16], o[18]), 0x35863586u);
#pragma unroll
          for (int r = 0; r < 2; r++) {
            const float ri = rcp_fast(__uint_as_float(r ? (den & 0xFFFF0000u) : (den << 16)));
            uint4 u;
            u.x = pk2(o[2 * r] * ri, o[2 * r + 1] * ri);
            u.y = pk2(o[4 + 2 * r] * ri, o[5 + 2 * r] * ri);
            u.z = pk2(o[8 + 2 * r] * ri, o[9 + 2 * r] * ri);
            u.w = pk2(o[12 + 2 * r] * ri, o[13 + 2 * r] * ri);
            if (hh == 0) st_cg4(ot + (64 * mt + 8 * r) * 8, u); else ov[2 * mt + r] = u;
          }
        }
        if (hh == 0) {
          __syncwarp();
          if (lane == 0) mbar_arrive(BAR(B_ODONE));
          if (elect) STAMP(wg, 10);
        }
      };
      auto trickle = [&](const int qs) {
        const int m = qs - 2 * (OCH + O1D) - (TRICK - 1);
        if (m >= 0 && m < 4) {
          st_cg4(ot + 8 * 1024 + (64 * (m >> 1) + 8 * (m & 1)) * 8, ov[m]);
          if (m == 3) { __syncwarp(); if (lane == 0) mbar_arrive(BAR(B_ODONE1)); }
        }
      };
#pragma unroll
      for (int i = 0; i < 4; i++) {
        const bool nx = i < 3;
        const int n = nx ? i + 1 : i;
        const uint32_t vo = (i & 1) ? OFF_H + (i >> 1) * 16384 : OFF_VP;
        if (2 * i == OCH) ocalc(0);
        if (2 * i == OCH + O1D) ocalc(1);
        if (nx) {
          conv_m1(K, ux, xl + n * (XT_STRIDE >> 4));
          conv_m1(K, uh, hl + (n >> 1) * 1024 + (n & 1) * 256);
        }
        if (2 * i != OCH && 2 * i != OCH + O1D) { if (nx) { if (i > 0) wg_wait<3>(); else wg_wait<2>(); } else wg_wait<1>(); }
        keepu(X[i][0]); keepu(X[i][1]); keepu(H[i][0]); keepu(H[i][1]);
        conv_win(K, X[i], W);
        trickle(4 * i);
        conv_pw<0>(W, H[i], V0, dil);
        conv_pw<1>(W, H[i], V1, dil);
        trickle(4 * i + 1);
        wg_wait<2>();
        if (i > 0) { keepu(y); YOUT(i - 1); }
        if (2 * i + 1 == OCH) ocalc(0);
        if (2 * i + 1 == OCH + O1D) ocalc(1);
        if (nx) {
          keepu(ux); keepu(uh);
          if (lane == 0) mbar_arrive_cl(BAR(B_XFREE + 4 * wg + n), rank ^ 1);
          conv_s2(K, ux, X[n], dfl);
          wg_wait<1>();
        } else wg_wait<0>();
        keepu(V0); keepu(V1);
        if (G2E && G2P == 0 && i == 3) { mbar_wait(BAR(B_FULL2), 0); G2_MMA(a0 + (SLOT_A & 15) * 1024, b0 + (SLOT_B & 15) * 1024, true); }
        trickle(4 * i + 2);
        if (i == 0) mbar_wait(BAR(B_H2), 0);
        conv_it<0>(K, V0, vst + vo);
        conv_it<1>(K, V1, vst + vo);
        if (G2E && G2P == 1 && i == 3) { mbar_wait(BAR(B_FULL2), 0); G2_MMA(a0 + (SLOT_A & 15) * 1024, b0 + (SLOT_B & 15) * 1024, true); }
        bar_sync(1 + wg);
#pragma unroll
        for (int s = 0; s < 4; s++) ldsm4t(a[s], vld + vo + s * 512);
        if (nx) conv_s2(K, uh, H[n], dfl);
        conv_m4(y, a, d4l);
        trickle(4 * i + 3);
        if (i > 0 && lane < 2) mbar_arrive_cl(BAR(B_AFREE + i - 1), lane);
        if (elect && i < 3) STAMP(wg, i < 2 ? 6 + i : 9 + i);
      }
      if (G2E && G2P == 2) { mbar_wait(BAR(B_FULL2), 0); G2_MMA(a0 + (SLOT_A & 15) * 1024, b0 + (SLOT_B & 15) * 1024, true); wg_wait<1>(); }
      else wg_wait<0>();
      keepu(y);
      if (G2E && G2P < 2 && rel) asm volatile("mbarrier.arrive.shared::cluster.b64 _, [%0];" ::"r"(cons) : "memory");
      YOUT(3);
      __syncwarp();
      if (lane == 0) mbar_arrive(BAR(B_Y));
      if (elect) STAMP(wg, 12);
    }
    {
      uint64_t ta = SLOT_A >> (4 * G2E), tb = SLOT_B >> (4 * G2E);
      uint32_t da = a0 + ((uint32_t)ta & 15) * 1024, db = b0 + ((uint32_t)tb & 15) * 1024, fb = BAR(B_FULL2 + G2E);
#pragma unroll 1
      for (int kb = G2E; kb < HOLD2; kb++) {
        mbar_wait(fb, 0);
        if (kb == G2E && elect) { STAMP(wg, 13); GSTAMP(wg, 28); }
        G2_MMA(da, db, kb == 0);
        ta >>= 4; tb >>= 4;
        da = a0 + ((uint32_t)ta & 15) * 1024; db = b0 + ((uint32_t)tb & 15) * 1024; fb += 8;
        asm volatile("" : "+r"(da), "+r"(db));
        wg_wait<1>();
        if ((kb > G2E || (G2E && G2P == 2)) && kb < 12 && rel) asm volatile("mbarrier.arrive.shared::cluster.b64 _, [%0];" ::"r"(cons) : "memory");
        cons += 8;
      }
#pragma unroll
      for (int kb = HOLD2; kb < 16; kb++) {
        if (wg == 1) mbar_wait(BAR(B_FULL2 + kb), 0);
        else if (kb == HOLD2) asm volatile("bar.sync 3, 256;" ::: "memory");
        G2_MMA(a0 + ((SLOT_A >> (4 * kb)) & 15) * 1024, b0 + ((SLOT_B >> (4 * kb)) & 15) * 1024, false);
      }
      if (wg == 1) asm volatile("bar.arrive 3, 256;" ::: "memory");
      const uint32_t stg = sb + wg * 8192 + w * 2048, so0 = ((SLOT_A >> 56) & 15) * 16384, so1 = ((SLOT_A >> 60) & 15) * 16384;
      const uint32_t lrow = stg + (8 * ((lane >> 3) & 1) + (lane & 7)) * 128 + (((lane >> 4) ^ (lane & 7)) << 4);
      const int col = 1024 + 256 * cb + 128 * rank, row = 128 * rb + 64 * wg + 16 * w;
      wg_wait<0>();
      keep(acc);
      if (elect) { STAMP(wg, 14); GSTAMP(wg, 29); }
#pragma unroll
      for (int cp = 0; cp < 8; cp++) {
        const float* a = &acc[8 * cp];
        stsm4((lrow ^ ((cp & 3) * 32)) + (cp >> 2 ? so1 : so0), pk2(a[0], a[1]), pk2(a[2], a[3]), pk2(a[4], a[5]), pk2(a[6], a[7]));
        if ((cp & 3) == 3) {
          fence_async();
          __syncwarp();
          if (elect_one()) tma2d_st(&P.tmOB, stg + (cp >> 2 ? so1 : so0), col + (cp >> 2) * 64, row);
        }
      }
      asm volatile("cp.async.bulk.commit_group;\ncp.async.bulk.wait_group.read 0;" ::: "memory");
      if (elect) {
        STAMP(wg, 15); GSTAMP(wg, 31); PDUMP(wg); if (wg == 0) PDUMP(2);
      }
    }
  } else {
    asm volatile("setmaxnreg.dec.sync.aligned.u32 56;");
    const int hw = warp - 9, g = lane >> 2, q = lane & 3;
#define sbar (bars + 8 * (B_STG - 18) + 16 * warp)
    if (warp == 8) {
      if (D1) __nanosleep(D1);
      int st = 1, pp = 1;
      const uint8_t* pfx = (const uint8_t*)P.x + (mb * 256 + hp * 16 + (lane & 15)) * 2048;
      const uint8_t* pfw = (const uint8_t*)P.w + (mb * 8 + (lane & 7)) * 6144 + (lane >> 3) * 2048 + hp * 128;
#pragma unroll 1
      for (int kb = 1; kb < 16; kb++) {
        if (kb >= 3) mbar_wait(BAR(B_EMPTY1 + st), pp);
        const uint32_t sa = sb + st * STAGE_BYTES;
        if (elect_one()) {
          mbar_expect(BAR(B_FULL1 + st), STAGE_BYTES);
          tma2d_mc(sa + rank * 16384, &P.tmX, kb * 64, mb * 256 + rank * 128, BAR(B_FULL1 + st));
          tma3d(sa + 32768, &P.tmW, hp * 64, kb * 64, 0, BAR(B_FULL1 + st));
        }
        if (kb == 1 && lane == 0) STAMP(2, 24);
        if (PFD && kb >= 2) {
#pragma unroll 1
          for (int j = kb == 2 ? 3 : kb + PFD; j <= kb + PFD && j < 16; j++) {
            if (lane < 16) asm volatile("prefetch.global.L2 [%0];" ::"l"(pfx + j * 128));
            if (lane < 24) asm volatile("prefetch.global.L2 [%0];" ::"l"(pfw + j * (64 * 6144)));
          }
          if (kb >= QPF && kb < QPF + 8) asm volatile("prefetch.global.L2 [%0];" ::"l"((const uint8_t*)P.q + (blockIdx.x * 256 + (kb - QPF) * 32 + lane) * 128));
          if (kb >= 4)
            asm volatile("prefetch.global.L2 [%0];" ::"l"(kb < 12 ? (const uint8_t*)P.h + ((2 * cl + rank) * 256 + (kb - 4) * 32 + lane) * 128
                                                                  : (const uint8_t*)P.wo + (blockIdx.x * 128 + (kb - 12) * 32 + lane) * 128));
        }
        if (++st == 3) { st = 0; pp ^= 1; }
      }
      if (lane == 0) STAMP(2, 1);
    } else {
      {
        const uint32_t clk0 = __shfl_sync(~0u, (uint32_t)clock(), 0), stg = sb + OFF_STG + hw * STG_STRIDE;
        const unsigned epoch = __shfl_sync(~0u, EPOCH, 0);
        const uint32_t tag = ~epoch & 1;
        uint32_t tap[2][4];
#pragma unroll
        for (int cg = 0; cg < 2; cg++) {
          const uint2 u = __ldg((const uint2*)(P.shift_k + (16 * cl + 8 * cg + g) * 4));
          tap[cg][0] = __byte_perm(u.x, 0, 0x1010); tap[cg][1] = __byte_perm(u.x, 0, 0x3232);
          tap[cg][2] = __byte_perm(u.y, 0, 0x1010); tap[cg][3] = __byte_perm(u.y, 0, 0x3232);
        }
        if (hw == 0 && lane < 8) *(float*)(smem + OFF_D + 4 * lane) = __bfloat162float(P.D[16 * cl + 8 * rank + lane]);
        if (hw == 1 && lane < 24) asm volatile("prefetch.global.L2 [%0];" ::"l"(P.thr + (lane + 24 * rank) * 32));
        if (hw == 0 && elect_one()) {
          *(volatile unsigned*)(smem + OFF_EPOCH) = epoch;
          mbar_expect(BAR(B_XRAW), 16384);
          mbar_expect(BAR(B_Y), 16384 + 64);
        }
#pragma unroll 1
        for (int i = hw * 32 + lane; i < 528; i += 96) st_tag4(P.part + (hp * 8 + mb) * 2176 + 4 * i, 0.f, 0.f, 0.f, 0.f, tag ^ 1);
        if (hw < 2 || lane < 2) st_tag4(P.kv + hp * 2176 + (4 * (hw < 2 ? 64 * mb + 32 * hw + lane : 512 + 8 * (mb & 1) + (mb & 6) + lane)), 0.f, 0.f, 0.f, 0.f, tag ^ 1);
        if (lane == 0) STAMP(3, hw);
        const uint32_t xo = sb + OFF_XT + g * XT_STRIDE + rank * 2048 + q * 4;
        const int krow = 8 + (lane & 7) - (lane >> 3);
        const uint32_t ka = stg + krow * 32 + ((krow & 4) << 2), va = stg + 2304 + lane * 32 + ((lane & 4) << 2);
        int ph = 0, b = 0;
#pragma unroll 1
        for (int ci = hw - 3; ci < 16; ci += 3) {
          const uint32_t bo = b ? OFF_F2F - OFF_STG : 0, bn = b ? 0 : OFF_F2F - OFF_STG;
          if (ci + 3 < 16) {
            while (__any_sync(~0u, (uint32_t)clock() - clk0 < HSTART + (ci + 3) * PACE)) __nanosleep(64);
            if (elect_one()) {
              mbar_expect(sbar + 8 * (b ^ 1), 2304 + 2048);
              tma2d(stg + bn, &P.tmK, 16 * cl, 1024 * rank + 64 * (ci + 3) - 8, sbar + 8 * (b ^ 1));
              tma2d(stg + bn + 2304, &P.tmV, 16 * cl, 1024 * rank + 64 * (ci + 3), sbar + 8 * (b ^ 1));
            }
          }
          if (ci >= 0) {
            mbar_wait(sbar + 8 * b, (ph >> b) & 1);
            ph ^= 1 << b;
#pragma unroll 1
            for (int grp = 0; grp < 2; grp++) {
#pragma unroll
              for (int cg = 0; cg < 2; cg++) {
                const uint32_t dst = mapa(xo + (ci >> 3) * 1024 + ((ci & 7) * 4 + 2 * grp) * 16, cg), xbar = mapa(BAR(B_XRAW), cg);
                uint32_t vv[4], kk[4][4];
                ldsm4t(vv, (va ^ (cg * 16)) + bo + grp * 1024);
#pragma unroll
                for (int rg = 0; rg < 4; rg++) ldsm4t(kk[rg], (ka ^ (cg * 16)) + bo + grp * 1024 + rg * 256);
#pragma unroll
                for (int rg = 0; rg < 4; rg++)
                  vv[rg] = hmul(hadd(hadd(hadd(hmul(kk[rg][3], tap[cg][3]), hmul(kk[rg][2], tap[cg][2])), hmul(kk[rg][1], tap[cg][1])), hmul(kk[rg][0], tap[cg][0])), vv[rg]);
                if (cg == rank) {
#pragma unroll
                  for (int rg = 0; rg < 4; rg++) asm volatile("st.shared.b32 [%0], %1;" ::"r"(dst + (rg & 1) * 512 + (rg >> 1) * 16), "r"(vv[rg]) : "memory");
                } else {
#pragma unroll
                  for (int rg = 0; rg < 4; rg++) st_async(dst + (rg & 1) * 512 + (rg >> 1) * 16, vv[rg], xbar);
                }
              }
            }
          }
          b ^= 1;
        }
      }
      if (lane == 0 && hw == 0) STAMP(3, 3);
      asm volatile("bar.sync 4, 96;" ::: "memory");
      if (hw == 0 && elect_one()) { mbar_expect(BAR(B_XT), 10240); bulk_ld(sb + OFF_F2F, P.img, 10240, BAR(B_XT)); }
      mbar_wait(BAR(B_XRAW), 0);
    }
    int e1 = 0;
#pragma unroll 1
    for (int n = hw < 0 ? 3 : 0; n < 4; n++) {
      const bool isH = n >= 3;
      const int c = isH ? (warp & 1) + 2 * (warp & 2) : hw + 3 * n;
      if (c < 8) {
        int ln;
        asm volatile("mov.u32 %0, %%laneid;" : "=r"(ln));
        uint8_t* dst = smem + (isH ? OFF_H + (c & 2) * 8192 + (c >> 2) * 8192 + (c & 1) * 4096 : OFF_XT + c * XT_STRIDE) + ((ln >> 4) * 512 + (ln & 15) * 16);
        const uint8_t* src0 = isH ? (const uint8_t*)P.h + (16 * cl + 8 * rank + c) * 4096 + ((ln & 15) * 32 + (ln & 16)) : dst;
        const uint8_t* src1 = src0 + (isH ? 512 : 256);
        uint32_t v[32];
#pragma unroll
        for (int i = 0; i < 8; i++) {
          const uint4 u = *(const uint4*)(((i & 1) ? src1 : src0) + (i >> 1) * 1024);
          v[4 * i] = u.x; v[4 * i + 1] = u.y; v[4 * i + 2] = u.z; v[4 * i + 3] = u.w;
        }
        if (isH) mbar_wait(BAR(B_XT), 0);
        const float f0 = __uint_as_float(v[0] << 16) + ((isH && ln == 0) ? *(const float*)(smem + OFF_D + 4 * c) : 0.f);
        const int e = norm_exp(v, f0);
        norm_cvt(v, f0, e);
        if (isH) mbar_wait(BAR(B_SFREE), 0);
        else if (ln == 0) smem[OFF_EX + c] = e;
        e1 = e;
#pragma unroll
        for (int i = 0; i < 8; i++)
          *(uint4*)(dst + (i >> 1) * 1024 + (i & 1) * 256) = make_uint4(v[4 * i], v[4 * i + 1], v[4 * i + 2], v[4 * i + 3]);
        if (n < 2 && elect_one()) {
          if (n == 0) mbar_expect(sbar, 4096);
          tma3d(sb + OFF_STG + 2048 * c, &P.tmQ, 16 * cl, 64 * rank, 2 * c, sbar);
        }
      }
      if (n >= 2) {
        fence_async();
        __syncwarp();
        if (lane == 0) { mbar_arrive(BAR(isH ? B_H : B_XT)); STAMP(3, (isH ? 17 : 13) + hw); }
      }
    }
#define SLOT(tab, kb) (sb + ((uint32_t)((tab) >> (4 * (kb))) & 15) * 16384)
#define KT(kb) (!OLOC ? (kb) : (kb) == 0 ? hq : (kb) == hq ? 0 : (kb))
#define LOAD_B(kb) tma4d(SLOT(SLOT_B, kb), &P.tmWo, 0, ((kb) >> 3) * 32, 2 * (KT(kb) & 7), 4 * cb + 2 * rank, BAR(B_FULL2 + (kb)))
#define LOAD_A(kb) bulk_ld_mc(SLOT(SLOT_A, kb) + rank * 8192, P.o + rb * OBLK + KT(kb) * 1024 + rank * 512, 8192, BAR(B_FULL2 + (kb)))
    asm volatile("setmaxnreg.inc.sync.aligned.u32 %0;" ::"n"(504 - 2 * RC));
    {
    int tid;
    asm volatile("mov.u32 %0, %%tid.x;" : "=r"(tid));
    const int lane = tid & 31, g = lane >> 2, q = lane & 3;
    const unsigned epoch = *(volatile unsigned*)(smem + OFF_EPOCH);
    const uint32_t tag = ~epoch & 1;
    const int pi = hw < 2 ? 64 * mb - 288 + tid : 512 + 8 * (mb & 1) + (mb & 6) + (lane & 1);
    const float* psrc = P.part + hp * 8 * 2176 + 4 * pi;
    uint4 f[8];
    {
      const uint32_t s16 = (sb & 0x3FFFF) >> 4;
      const int t = tid & 127, c = 2 + (warp & 1) + 2 * (warp & 2);
      const uint4* hp4 = (const uint4*)(P.h + (16 * cl + 8 * rank + c) * 2048) + ((lane & 15) * 2 + (lane >> 4));
      uint32_t v[32];
#pragma unroll
      for (int i = 0; i < 8; i++) { const uint4 u = ld_na4(hp4 + i * 32); v[4 * i] = u.x; v[4 * i + 1] = u.y; v[4 * i + 2] = u.z; v[4 * i + 3] = u.w; }
      float kva[36];
#pragma unroll
      for (int mt = 0; mt < 2; mt++) {
        mbar_wait(BAR(B_PKRDY + mt), 0);
        wg_fence();
#pragma unroll
        for (int ks = 0; ks < 8; ks++) {
          const uint32_t o = (ks >> 2) * 1024 + mt * 512 + (ks & 3) * 128, vb = (2 * STAGE_BYTES >> 4) + o;
          wgmma_ss_n72<1, 1>(kva, dsc(s16 + o + (1 << 16), SW128), dsc(s16 + vb + (((OFF_ONES >> 4) - vb) << 16), SW128), (mt | ks) != 0);
        }
        wg_commit();
        if (mt == 0 && hw < 0) {
          mbar_wait(BAR(B_G1DONE), 0);
          if (elect_one()) {
#pragma unroll
            for (int kb = 0; kb < BEARLY; kb++) { mbar_expect(BAR(B_FULL2 + kb), 16384); LOAD_B(kb); }
          }
        }
      }
      float* pdst = P.part + (hp * 8 + mb) * 2176 + t * 4;
      float* zdst = P.part + (hp * 8 + mb) * 2176 + 2048 + (t >> 1);
      asm volatile("" : "+l"(pdst), "+l"(zdst));
      wg_wait<0>();
      keep(kva);
      if (hw < 1) {
#pragma unroll
        for (int c = 0; c < 4; c++) st_tag4(pdst + c * 512, kva[4 * c], kva[4 * c + 1], kva[4 * c + 2], kva[4 * c + 3], tag);
      } else {
#pragma unroll
        for (int c = 4; c < 8; c++) st_tag4(pdst + (c - 4) * 512, kva[4 * c], kva[4 * c + 1], kva[4 * c + 2], kva[4 * c + 3], tag);
      }
      const float z2 = __shfl_down_sync(~0u, kva[32], 4), z3 = __shfl_down_sync(~0u, kva[34], 4);
      if (!(lane & 7)) st_tag4(zdst, kva[32], kva[34], z2, z3, tag);
      if (lane == 0) mbar_arrive(BAR(B_PKFREE));
      const uint32_t cst = clock();
      if (hw == 0 && lane == 0) STAMP(3, 24);
      const float f0 = __uint_as_float(v[0] << 16) + (lane == 0 ? *(const float*)(smem + OFF_D + 4 * c) : 0.f);
      const int e = norm_exp(v, f0);
      norm_cvt(v, f0, e);
      if (hw >= 0) {
        while (__any_sync(~0u, (uint32_t)clock() - cst < PD1)) __nanosleep(20);
        if (hw == 0 && lane == 0) STAMP(3, 20);
#pragma unroll
        for (int p = 0; p < 8; p++) f[p] = ld_rlx4(psrc + p * 2176);
      }
      uint8_t* dst = smem + OFF_H + 16384 + (warp & 3) * 4096 + (lane >> 4) * 512 + (lane & 15) * 16;
#pragma unroll
      for (int i = 0; i < 8; i++)
        *(uint4*)(dst + (i >> 1) * 1024 + (i & 1) * 256) = make_uint4(v[4 * i], v[4 * i + 1], v[4 * i + 2], v[4 * i + 3]);
      if (lane < 4) {
        const int cc = c - (lane & 2);
        st_async(mapa(sb + OFF_SCALE + (8 * rank + cc) * 4, lane & 1), min(max(((lane & 2) ? e1 : e) + smem[OFF_EX + cc] - 124, 1), 254) << 23, mapa(BAR(B_Y), lane & 1));
      }
    }
#define H2_READY() do { fence_async(); __syncwarp(); if (lane == 0) mbar_arrive(BAR(B_H2)); } while (0)
    if (warp == 8) {
      H2_READY();
      mbar_wait(BAR(B_PKFREE), 0);
      {
        const uint32_t c0 = clock();
#pragma unroll 1
        for (int i = 0; i < 2 * NPRE - 2 * BEARLY; i++) {
          const int kb = (i >> 1) + BEARLY;
          while (__any_sync(~0u, (uint32_t)clock() - c0 < i * BPACE)) __nanosleep(32);
          if (elect_one()) {
            if (!(i & 1)) mbar_expect(BAR(B_FULL2 + kb), 16384);
            tma4d(SLOT(SLOT_B, kb) + (i & 1) * 8192, &P.tmWo1, 0, 0, 2 * KT(kb), 4 * cb + 2 * rank + (i & 1), BAR(B_FULL2 + kb));
            if (i == 0) mbar_expect(BAR(B_Q), 8192);
            if (i < 4) tma3d(sb + OFF_SPARE + 2048 * i, &P.tmQ, 16 * cl, 64 * rank + 32 * (i >> 1), 2 * ((i + 6) & 7), BAR(B_Q));
          }
        }
      }
      if (lane == 0) STAMP(2, 2);
      if (OLOC) {
        if (elect_one()) mbar_expect(BAR(B_FULL2), 16384);
        mbar_wait(BAR(B_OLOC), 0);
        asm volatile("fence.acquire.cluster;\nfence.proxy.async.global;" ::: "memory");
        if (elect_one()) LOAD_A(0);
      }
      mbar_wait(BAR(B_AFREE), 0);
      if (elect_one()) mbar_expect(BAR(B_FULL2 + OLOC), 16384);
      {
        const uint32_t dst = SLOT(SLOT_A, OLOC) + rank * 8192;
        const uint4* src = P.o + rb * OBLK + KT(OLOC) * 1024 + rank * 512;
        poll_ge(OCNT(rb, 0), 16 * (epoch + 1));
        asm volatile("fence.proxy.async.global;" ::: "memory");
        if (lane == 0) STAMP(2, 3);
        if (elect_one()) bulk_ld_mc(dst, src, 8192, BAR(B_FULL2 + OLOC));
        if (lane == 0) STAMP(3, 23);
      }
#pragma unroll 1
      for (int kb = 1 + OLOC; kb < NPRE; kb++) {
        mbar_wait(BAR(kb < 4 ? B_AFREE + kb - 1 : B_CONS2), 0);
        if (elect_one()) { mbar_expect(BAR(B_FULL2 + kb), 16384); LOAD_A(kb); }
      }
#pragma unroll 1
      for (int kb = NPRE; kb < 16; kb++) {
        mbar_wait(BAR(B_CONS2 + kb - 5), 0);
        if (kb == 8) mbar_wait(BAR(B_O1RDY), 0);
        if (elect_one()) { mbar_expect(BAR(B_FULL2 + kb), 32768); LOAD_A(kb); LOAD_B(kb); }
      }
      if (lane == 0) { EPOCH = epoch + 1; STAMP(2, 5); }
    } else {
      {
#pragma unroll 1
        for (int n = 0; __any_sync(~0u, stale8(f, tag) & 1); n++) {
#pragma unroll
          for (int p = 0; p < 8; p++) ld_stale4(f[p], psrc + p * 2176, tag);
          if (n > SPIN_LIMIT) __trap();
        }
        float s0 = 0.f, s1 = 0.f, s2 = 0.f, s3 = 0.f;
#pragma unroll
        for (int p = 0; p < 8; p++) { s0 += __uint_as_float(f[p].x); s1 += __uint_as_float(f[p].y); s2 += __uint_as_float(f[p].z); s3 += __uint_as_float(f[p].w); }
        if (hw < 2 || lane < 2) st_tag4(P.kv + hp * 2176 + (4 * pi), s0, s1, s2, s3, tag);
      }
      const uint32_t cs2 = clock();
      if (lane == 0 && hw == 0) STAMP(3, 8);
      H2_READY();
      if (hw == 2) {
        unsigned* cnt = OCNT(2 * mb + lane, 0);
#pragma unroll 1
        for (int hh = 0; hh < 2; hh++) {
          mbar_wait(BAR(hh ? B_ODONE1 : B_ODONE), 0);
          if (lane < 2) asm volatile("red.release.gpu.global.add.u32 [%0], 1;" ::"l"(cnt) : "memory");
          if (OLOC && hh == 0 && lane < 2) mbar_arrive_cl(BAR(B_OLOC), lane);
          cnt += 32;
          if (lane == 0) STAMP(3, hh ? 6 : 7);
        }
        poll_ge(OCNT(rb, 1), 16 * (epoch + 1));
        asm volatile("fence.proxy.async.global;" ::: "memory");
        if (lane == 0) { mbar_arrive(BAR(B_O1RDY)); STAMP(2, 4); }
        __syncwarp();
      } else {
        const int t = tid - 288;
        const float* src = P.kv + hp * 2176 + 4 * (t + 32 * hw);
        const float* zsrc = P.kv + hp * 2176 + (2048 + (t & 48) + 2 * (lane & 6));
        mbar_wait(BAR(B_PKFREE), 0);
        while (__any_sync(~0u, (uint32_t)clock() - cs2 < PD2)) __nanosleep(20);
        uint4 zp = ld_rlx4(zsrc);
#pragma unroll
        for (int p = 0; p < 8; p++) f[p] = ld_rlx4(src + 4 * ((p & 3) * 128 + (p >> 2) * 32));
        if (!opaque_true()) __trap();
#pragma unroll 1
        for (int n = 0; __any_sync(~0u, (stale8(f, tag) | (zp.x ^ tag)) & 1); n++) {
          ld_stale4(zp, zsrc, tag);
#pragma unroll
          for (int p = 0; p < 8; p++) ld_stale4(f[p], src + 4 * ((p & 3) * 128 + (p >> 2) * 32), tag);
          if (n > SPIN_LIMIT) __trap();
        }
#define PK2U(a, b) pk2(__uint_as_float(a), __uint_as_float(b))
        const uint32_t zf = (lane & 1) ? ((lane & 8) ? zp.w : zp.z) : ((lane & 8) ? zp.y : zp.x);
        const uint32_t zz = PK2U(zf, zf);
        *(uint4*)(smem + OFF_KVB + hw * 2560 + 2048 + lane * 16) = make_uint4(zz, zz, zz, zz);
#pragma unroll
        for (int hh = 0; hh < 2; hh++) {
          const uint4* ff = &f[4 * hh];
          uint8_t* dst = smem + OFF_KVB + hw * 2560 + q * 512 + (16 * hh + g) * 16;
          *(uint4*)dst = make_uint4(PK2U(ff[0].x, ff[0].y), PK2U(ff[1].x, ff[1].y), PK2U(ff[2].x, ff[2].y), PK2U(ff[3].x, ff[3].y));
          *(uint4*)(dst + 128) = make_uint4(PK2U(ff[0].z, ff[0].w), PK2U(ff[1].z, ff[1].w), PK2U(ff[2].z, ff[2].w), PK2U(ff[3].z, ff[3].w));
        }
        fence_async();
        __syncwarp();
        if (lane == 0) { mbar_arrive(BAR(hw ? B_KV1 : B_KV)); if (hw == 0) STAMP(3, 9); }
      }
#define QBUF(ci) (sb + 2048 * (ci) + ((ci) < 6 ? OFF_STG : (ci) < 10 ? OFF_SPARE - 6 * 2048 : OFF_F2F - 10 * 2048))
      mbar_wait(BAR(B_Y), 0);
      if (elect_one()) {
        mbar_expect(sbar + 8, 4096);
#pragma unroll 1
        for (int ci = hw ? hw + 9 : 12; ci < 16; ci += 3) tma3d(QBUF(ci), &P.tmQ, 16 * cl, 64 * rank + 32, 2 * (ci & 7), sbar + 8);
      }
      mbar_wait(BAR(B_Q), 0);
      mbar_wait(sbar, hw == 0);
      {
        const float2 sc0 = *(const float2*)(smem + OFF_SCALE + 8 * q), sc1 = *(const float2*)(smem + OFF_SCALE + 32 + 8 * q);
        const uint32_t yl = sb + OFF_XT + (lane & 7) * XT_STRIDE + (lane >> 3) * 16;
#pragma unroll 1
        for (int ci = hw; ci < 16; ci += 3) {
          const uint32_t qb = QBUF(ci);
          if (ci >= 10) mbar_wait(sbar + 8, 1);
#pragma unroll 1
          for (int nl = 0; nl < 2; nl++) {
            uint32_t yy[2][4], qq[2][4];
            const uint32_t qa = qb + lane * 32 + ((lane & 4) << 2) + nl * 1024;
#pragma unroll
            for (int cg = 0; cg < 2; cg++) { ldsm4t(yy[cg], yl + cg * 2048 + (2 * ci + nl) * 64); ldsm4(qq[cg], qa ^ (cg * 16)); }
#pragma unroll
            for (int cg = 0; cg < 2; cg++) {
              const float2 sc = cg ? sc1 : sc0;
#pragma unroll
              for (int m = 0; m < 4; m++) {
                const float2 f = __half22float2(*(const __half2*)&yy[cg][m]);
                qq[cg][m] = hmul(qq[cg][m], pk2(f.x * sc.x, f.y * sc.y));
              }
              stsm4(qa ^ (cg * 16), qq[cg][0], qq[cg][1], qq[cg][2], qq[cg][3]);
            }
          }
          fence_async();
          __syncwarp();
          if (elect_one()) tma3d_st(&P.tmOA, qb, 16 * cl, 64 * rank + 32 * (ci >> 3), 2 * (ci & 7));
        }
        asm volatile("cp.async.bulk.commit_group;\ncp.async.bulk.wait_group.read 0;" ::: "memory");
      }
      if (lane == 0) STAMP(3, 10 + hw);
    }
    }
  }
}

typedef CUresult (*EncodeFn)(CUtensorMap*, CUtensorMapDataType, cuuint32_t, void*, const cuuint64_t*, const cuuint64_t*,
                             const cuuint32_t*, const cuuint32_t*, CUtensorMapInterleave, CUtensorMapSwizzle,
                             CUtensorMapL2promotion, CUtensorMapFloatOOBfill);

static void enc(EncodeFn fn, CUtensorMap* m, const void* p, int rank, const cuuint64_t* dims, const cuuint64_t* strides,
                const cuuint32_t* box, CUtensorMapSwizzle swz, CUtensorMapL2promotion promo) {
  cuuint32_t es[4] = {1, 1, 1, 1};
  fn(m, CU_TENSOR_MAP_DATA_TYPE_BFLOAT16, rank, (void*)p, dims, strides, box, es, CU_TENSOR_MAP_INTERLEAVE_NONE, swz, promo,
     CU_TENSOR_MAP_FLOAT_OOB_FILL_NONE);
}

extern "C" void kernel_launch(void* const* d_in, const int* in_sizes, int n_in, void* d_out, int out_size) {
  void* fp = nullptr;
  cudaDriverEntryPointQueryResult qr;
  cudaGetDriverEntryPoint("cuTensorMapEncodeTiled", &fp, cudaEnableDefault, &qr);
  EncodeFn fn = (EncodeFn)fp;
  Params P;
  P.shift_k = (const __nv_bfloat16*)d_in[3]; P.h = (const __nv_bfloat16*)d_in[4]; P.D = (const __nv_bfloat16*)d_in[5];
  P.q = (const __nv_bfloat16*)d_in[0];
  cudaGetSymbolAddress((void**)&P.part, g_part); cudaGetSymbolAddress((void**)&P.kv, g_kv); cudaGetSymbolAddress((void**)&P.o, g_o);
  cudaGetSymbolAddress((void**)&P.thr, c_thr); cudaGetSymbolAddress((void**)&P.img, c_img);
  P.x = (const __nv_bfloat16*)d_in[6]; P.w = (const __nv_bfloat16*)d_in[7]; P.wo = (const __nv_bfloat16*)d_in[8];
  const CUtensorMapSwizzle S128 = CU_TENSOR_MAP_SWIZZLE_128B, S32 = CU_TENSOR_MAP_SWIZZLE_32B;
  const CUtensorMapL2promotion P0 = CU_TENSOR_MAP_L2_PROMOTION_NONE, P128 = CU_TENSOR_MAP_L2_PROMOTION_L2_128B;
  { cuuint64_t d[2] = {1024, 2048}, s[1] = {2048}; cuuint32_t b[2] = {64, 128}; enc(fn, &P.tmX, d_in[6], 2, d, s, b, S128, P128); }
  { cuuint64_t d[2] = {1024, 2048}, s[1] = {2048}; cuuint32_t b[2] = {64, 64}; enc(fn, &P.tmX0, d_in[6], 2, d, s, b, S128, P128); }
  { cuuint64_t d[3] = {1024, 1024, 3}, s[2] = {6144, 2048}; cuuint32_t b[3] = {64, 64, 3}; enc(fn, &P.tmW, d_in[7], 3, d, s, b, S128, P128); }
  { cuuint64_t d[4] = {64, 64, 16, 16}, s[3] = {2048, 131072, 128}; cuuint32_t b[4] = {64, 32, 2, 2}; enc(fn, &P.tmWo, d_in[8], 4, d, s, b, S128, P128); }
  { cuuint64_t d[4] = {64, 64, 16, 16}, s[3] = {2048, 131072, 128}; cuuint32_t b[4] = {64, 32, 2, 1}; enc(fn, &P.tmWo1, d_in[8], 4, d, s, b, S128, P128); }
  { cuuint64_t d[2] = {1024, 2048}, s[1] = {2048}; cuuint32_t b[2] = {16, 72}; enc(fn, &P.tmK, d_in[1], 2, d, s, b, S32, P128); }
  { cuuint64_t d[2] = {1024, 2048}, s[1] = {2048}; cuuint32_t b[2] = {16, 64}; enc(fn, &P.tmV, d_in[2], 2, d, s, b, S32, P128); }
  { cuuint64_t d[3] = {1024, 128, 16}, s[2] = {32768, 2048}; cuuint32_t b[3] = {16, 32, 2}; enc(fn, &P.tmQ, d_in[0], 3, d, s, b, S32, P128); }
  { cuuint64_t d[3] = {1024, 128, 16}, s[2] = {65536, 4096}; cuuint32_t b[3] = {16, 32, 2}; enc(fn, &P.tmOA, d_out, 3, d, s, b, S32, P0); }
  { cuuint64_t d[2] = {2048, 2048}, s[1] = {4096}; cuuint32_t b[2] = {64, 16}; enc(fn, &P.tmOB, d_out, 2, d, s, b, S128, P0); }
  cudaFuncSetAttribute(fused_kernel, cudaFuncAttributeMaxDynamicSharedMemorySize, SMEM_TOTAL);
  fused_kernel<<<128, 384, SMEM_TOTAL>>>(P);
}
```

```cpp
#include <cuda_runtime.h>
#include <cuda_bf16.h>
#include <cuda_fp16.h>
#include <cuda.h>
#include <stdint.h>

template<int TA, int TB, int SA=1> __device__ __forceinline__ void wgmma_ss_n192(float (&d)[96], uint64_t da, uint64_t db, int scale_d) {
  asm volatile("{\n.reg .pred p;\nsetp.ne.b32 p, %98, 0;\n"
    "wgmma.mma_async.sync.aligned.m64n192k16.f32.bf16.bf16 {%0, %1, %2, %3, %4, %5, %6, %7, %8, %9, %10, %11, %12, %13, %14, %15, %16, %17, %18, %19, %20, %21, %22, %23, %24, %25, %26, %27, %28, %29, %30, %31, %32, %33, %34, %35, %36, %37, %38, %39, %40, %41, %42, %43, %44, %45, %46, %47, %48, %49, %50, %51, %52, %53, %54, %55, %56, %57, %58, %59, %60, %61, %62, %63, %64, %65, %66, %67, %68, %69, %70, %71, %72, %73, %74, %75, %76, %77, %78, %79, %80, %81, %82, %83, %84, %85, %86, %87, %88, %89, %90, %91, %92, %93, %94, %95}, %96, %97, p, %101, 1, %99, %100;\n}\n"
    : "+f"(d[0]), "+f"(d[1]), "+f"(d[2]), "+f"(d[3]), "+f"(d[4]), "+f"(d[5]), "+f"(d[6]), "+f"(d[7]), "+f"(d[8]), "+f"(d[9]), "+f"(d[10]), "+f"(d[11]), "+f"(d[12]), "+f"(d[13]), "+f"(d[14]), "+f"(d[15]), "+f"(d[16]), "+f"(d[17]), "+f"(d[18]), "+f"(d[19]), "+f"(d[20]), "+f"(d[21]), "+f"(d[22]), "+f"(d[23]), "+f"(d[24]), "+f"(d[25]), "+f"(d[26]), "+f"(d[27]), "+f"(d[28]), "+f"(d[29]), "+f"(d[30]), "+f"(d[31]), "+f"(d[32]), "+f"(d[33]), "+f"(d[34]), "+f"(d[35]), "+f"(d[36]), "+f"(d[37]), "+f"(d[38]), "+f"(d[39]), "+f"(d[40]), "+f"(d[41]), "+f"(d[42]), "+f"(d[43]), "+f"(d[44]), "+f"(d[45]), "+f"(d[46]), "+f"(d[47]), "+f"(d[48]), "+f"(d[49]), "+f"(d[50]), "+f"(d[51]), "+f"(d[52]), "+f"(d[53]), "+f"(d[54]), "+f"(d[55]), "+f"(d[56]), "+f"(d[57]), "+f"(d[58]), "+f"(d[59]), "+f"(d[60]), "+f"(d[61]), "+f"(d[62]), "+f"(d[63]), "+f"(d[64]), "+f"(d[65]), "+f"(d[66]), "+f"(d[67]), "+f"(d[68]), "+f"(d[69]), "+f"(d[70]), "+f"(d[71]), "+f"(d[72]), "+f"(d[73]), "+f"(d[74]), "+f"(d[75]), "+f"(d[76]), "+f"(d[77]), "+f"(d[78]), "+f"(d[79]), "+f"(d[80]), "+f"(d[81]), "+f"(d[82]), "+f"(d[83]), "+f"(d[84]), "+f"(d[85]), "+f"(d[86]), "+f"(d[87]), "+f"(d[88]), "+f"(d[89]), "+f"(d[90]), "+f"(d[91]), "+f"(d[92]), "+f"(d[93]), "+f"(d[94]), "+f"(d[95])
    : "l"(da), "l"(db), "r"(scale_d), "n"(TA), "n"(TB), "n"(SA));
}
template<int TA, int TB, int SA=1> __device__ __forceinline__ void wgmma_ss_n128(float (&d)[64], uint64_t da, uint64_t db, int scale_d) {
  asm volatile("{\n.reg .pred p;\nsetp.ne.b32 p, %66, 0;\n"
    "wgmma.mma_async.sync.aligned.m64n128k16.f32.bf16.bf16 {%0, %1, %2, %3, %4, %5, %6, %7, %8, %9, %10, %11, %12, %13, %14, %15, %16, %17, %18, %19, %20, %21, %22, %23, %24, %25, %26, %27, %28, %29, %30, %31, %32, %33, %34, %35, %36, %37, %38, %39, %40, %41, %42, %43, %44, %45, %46, %47, %48, %49, %50, %51, %52, %53, %54, %55, %56, %57, %58, %59, %60, %61, %62, %63}, %64, %65, p, %69, 1, %67, %68;\n}\n"
    : "+f"(d[0]), "+f"(d[1]), "+f"(d[2]), "+f"(d[3]), "+f"(d[4]), "+f"(d[5]), "+f"(d[6]), "+f"(d[7]), "+f"(d[8]), "+f"(d[9]), "+f"(d[10]), "+f"(d[11]), "+f"(d[12]), "+f"(d[13]), "+f"(d[14]), "+f"(d[15]), "+f"(d[16]), "+f"(d[17]), "+f"(d[18]), "+f"(d[19]), "+f"(d[20]), "+f"(d[21]), "+f"(d[22]), "+f"(d[23]), "+f"(d[24]), "+f"(d[25]), "+f"(d[26]), "+f"(d[27]), "+f"(d[28]), "+f"(d[29]), "+f"(d[30]), "+f"(d[31]), "+f"(d[32]), "+f"(d[33]), "+f"(d[34]), "+f"(d[35]), "+f"(d[36]), "+f"(d[37]), "+f"(d[38]), "+f"(d[39]), "+f"(d[40]), "+f"(d[41]), "+f"(d[42]), "+f"(d[43]), "+f"(d[44]), "+f"(d[45]), "+f"(d[46]), "+f"(d[47]), "+f"(d[48]), "+f"(d[49]), "+f"(d[50]), "+f"(d[51]), "+f"(d[52]), "+f"(d[53]), "+f"(d[54]), "+f"(d[55]), "+f"(d[56]), "+f"(d[57]), "+f"(d[58]), "+f"(d[59]), "+f"(d[60]), "+f"(d[61]), "+f"(d[62]), "+f"(d[63])
    : "l"(da), "l"(db), "r"(scale_d), "n"(TA), "n"(TB), "n"(SA));
}
template<int TA, int TB, int SA=1> __device__ __forceinline__ void wgmma_ss_n72(float (&d)[36], uint64_t da, uint64_t db, int scale_d) {
  asm volatile("{\n.reg .pred p;\nsetp.ne.b32 p, %38, 0;\n"
    "wgmma.mma_async.sync.aligned.m64n72k16.f32.bf16.bf16 {%0, %1, %2, %3, %4, %5, %6, %7, %8, %9, %10, %11, %12, %13, %14, %15, %16, %17, %18, %19, %20, %21, %22, %23, %24, %25, %26, %27, %28, %29, %30, %31, %32, %33, %34, %35}, %36, %37, p, %41, 1, %39, %40;\n}\n"
    : "+f"(d[0]), "+f"(d[1]), "+f"(d[2]), "+f"(d[3]), "+f"(d[4]), "+f"(d[5]), "+f"(d[6]), "+f"(d[7]), "+f"(d[8]), "+f"(d[9]), "+f"(d[10]), "+f"(d[11]), "+f"(d[12]), "+f"(d[13]), "+f"(d[14]), "+f"(d[15]), "+f"(d[16]), "+f"(d[17]), "+f"(d[18]), "+f"(d[19]), "+f"(d[20]), "+f"(d[21]), "+f"(d[22]), "+f"(d[23]), "+f"(d[24]), "+f"(d[25]), "+f"(d[26]), "+f"(d[27]), "+f"(d[28]), "+f"(d[29]), "+f"(d[30]), "+f"(d[31]), "+f"(d[32]), "+f"(d[33]), "+f"(d[34]), "+f"(d[35])
    : "l"(da), "l"(db), "r"(scale_d), "n"(TA), "n"(TB), "n"(SA));
}
template<int TB, int SA=1> __device__ __forceinline__ void wgmma_rs_n40(float (&d)[20], uint32_t a0, uint32_t a1, uint32_t a2, uint32_t a3, uint64_t db, int scale_d) {
  asm volatile("{\n.reg .pred p;\nsetp.ne.b32 p, %25, 0;\n"
    "wgmma.mma_async.sync.aligned.m64n40k16.f32.bf16.bf16 {%0, %1, %2, %3, %4, %5, %6, %7, %8, %9, %10, %11, %12, %13, %14, %15, %16, %17, %18, %19}, {%20, %21, %22, %23}, %24, p, %27, 1, %26;\n}\n"
    : "+f"(d[0]), "+f"(d[1]), "+f"(d[2]), "+f"(d[3]), "+f"(d[4]), "+f"(d[5]), "+f"(d[6]), "+f"(d[7]), "+f"(d[8]), "+f"(d[9]), "+f"(d[10]), "+f"(d[11]), "+f"(d[12]), "+f"(d[13]), "+f"(d[14]), "+f"(d[15]), "+f"(d[16]), "+f"(d[17]), "+f"(d[18]), "+f"(d[19])
    : "r"(a0), "r"(a1), "r"(a2), "r"(a3), "l"(db), "r"(scale_d), "n"(TB), "n"(SA));
}
template<int TB> __device__ __forceinline__ void wgmma_hrs_n64(uint32_t (&d)[16], uint32_t a0, uint32_t a1, uint32_t a2, uint32_t a3, uint64_t db, int scale_d) {
  asm volatile("{\n.reg .pred p;\nsetp.ne.b32 p, %21, 0;\n"
    "wgmma.mma_async.sync.aligned.m64n64k16.f16.f16.f16 {%0, %1, %2, %3, %4, %5, %6, %7, %8, %9, %10, %11, %12, %13, %14, %15}, {%16, %17, %18, %19}, %20, p, 1, 1, %22;\n}\n"
    : "+r"(d[0]), "+r"(d[1]), "+r"(d[2]), "+r"(d[3]), "+r"(d[4]), "+r"(d[5]), "+r"(d[6]), "+r"(d[7]), "+r"(d[8]), "+r"(d[9]), "+r"(d[10]), "+r"(d[11]), "+r"(d[12]), "+r"(d[13]), "+r"(d[14]), "+r"(d[15])
    : "r"(a0), "r"(a1), "r"(a2), "r"(a3), "l"(db), "r"(scale_d), "n"(TB));
}
template<int TB> __device__ __forceinline__ void wgmma_hrs_n32(uint32_t (&d)[8], uint32_t a0, uint32_t a1, uint32_t a2, uint32_t a3, uint64_t db, int scale_d) {
  asm volatile("{\n.reg .pred p;\nsetp.ne.b32 p, %13, 0;\n"
    "wgmma.mma_async.sync.aligned.m64n32k16.f16.f16.f16 {%0, %1, %2, %3, %4, %5, %6, %7}, {%8, %9, %10, %11}, %12, p, 1, 1, %14;\n}\n"
    : "+r"(d[0]), "+r"(d[1]), "+r"(d[2]), "+r"(d[3]), "+r"(d[4]), "+r"(d[5]), "+r"(d[6]), "+r"(d[7])
    : "r"(a0), "r"(a1), "r"(a2), "r"(a3), "l"(db), "r"(scale_d), "n"(TB));
}

__device__ __align__(128) const uint32_t c_thr[1536] = {
  0x33fb33ff,0xa49c9de4,0x33273352,0xaf2cae76,0x33e233f1,0xa96ca7bd,0x32c432f7,0xb045afdd,0x33b733cf,0xac3eaaf7,0x3250328c,0xb0eab099,
  0x3378339a,0xadbcacff,0x31cd3211,0xb182b137,0x33d033fb,0xaadea46a,0x299e2d17,0xb3e0b396,0x32fb337a,0xafd2adb1,0xa78b1f76,0xb3f2b3ff,
  0x318b3254,0xb1c5b0e5,0xae6bac32,0xb354b3b8,0x2f4230a3,0xb321b285,0xb133b040,0xb215b2c7,0x337c33f2,0xada5a759,0xb179afc8,0xb1d6b2fe,
  0x31463293,0xb204b08e,0xb394b2ba,0xad23b055,0x2b402f4e,0xb3cbb31e,0xb3e4b3f9,0x293ba533,0xac269c52,0xb3bab400,0xb258b357,0x30e02e5f,
  0x330133e5,0xafbda922,0xb3f3b3c9,0x2727ab59,0x2deb314a,0xb36fb200,0xb194b32f,0x31bc2f0a,0xacdb2084,0xb39fb3ff,0xa565aea4,0x33f93347,
  0xb2b6b0db,0xb05ab25c,0x30892c1a,0x329733bc,0x326033d4,0xb0d6aa94,0xb00ab29b,0x32e83084,0x20e82f64,0xb3feb318,0x2d8da597,0x338133f8,
  0xb1fcae48,0xb14fb35c,0x339031b8,0x2d3a3199,0xb3e6b3ae,0x2909ac7b,0x32d133f4,0xb030a6f5,0x319d33bf,0xb1b3ac02,0x2e3ca874,0x335e33ec,
  0xacc32b89,0xb3a3b3c6,0x33f83276,0x25c930b7,0xb3dcb1f8,0xaa01b154,0x30653335,0xb2b0aef4,0xb107b383,0x32392d81,0xafa6214d,0xb307b3fe,
  0x30bc33a5,0xb273acb7,0x33c5311b,0x2ba23229,0xb0cc94b6,0xb267b400,0x30153360,0xb2e1ae31,0xb385b3ab,0x2d76ac93,0xb166a691,0xb1e7b3f5,
  0x22deb06a,0x33fd32ac,0xb337b3da,0x2ee8aa19,0x2f853387,0xb310ad6a,0x322d33fe,0xb1162216,0xb2a9abd3,0xb06fb3c2,0xb07428a6,0xb2a5b3ea,
  0xb111b3e9,0x323128be,0xb30db3c3,0x2f90abba,0x31aa227a,0x31a633fd,0x2e25ad5e,0x33633389,0x2d6a3365,0xb387ae1a,0xa21631aa,0xb3feb1a6,
  0xb3c2af85,0xabd3b310,0xb3eab22d,0x28a6b116,0xa8beb2a9,0x33e9306f,0x2bbab074,0x33c332a5,0x33fd3111,0x227a3231,0x3389330d,0xad5e2f90,
  0x2a63333f,0xb3d7aec6,0xb2a2a1b1,0xb07ab3fe,0xb3f7b158,0x25fbb1f4,0xacb7b38b,0x33a52d52,0x2e0eb025,0x336832d8,0x340030bc,0x14b63273,
  0x323533c0,0xb10c2beb,0xac9330cc,0xb3abb267,0x23433316,0xb3fdaf6f,0xb38eb225,0x2d46b11f,0xb342b29e,0x2ebbb07f,0x31e3aa7c,0x316b33d6,
  0x3264a6c3,0x30d133f5,0x2c0233ac,0xb3bfac87,0x28f0336a,0xb3e7ae02,0xb3c6b19d,0x2b89b1b3,0xa59732e8,0xb3f8b00a,0xaccfb3ed,0x33a1285b,
  0xb1b8b381,0x3199ad8d,0x336c31df,0xadf73170,0x33f42d3a,0x26f53390,0xb30423a7,0xafb2b3fc,0xb05f3030,0xb2b3b2d1,0x29e8b27a,0x33dd30b2,
  0xab5932b6,0xb3c9b05a,0x30adb089,0x327e3297,0xaf0ab3f3,0x332fa727,0x240633b0,0xb3fcac6f,0x33473194,0xaea431bc,0xb174b359,0x31daae54,
  0xb3bca565,0xac1ab3f9,0x33ee2f59,0xa842331b,0xaddf3281,0xb371b0a8,0x34002b40,0x1c5233cb,0xa759b3ef,0x33f22829,0xb2fe2c26,0xafc8b3ba,
  0x308e337c,0xb2932da5,0x3055b179,0x32ba31d6,0xb31eb146,0x2f4eb204,0xa5333394,0xb3f9ad23,0xaff33249,0xb2f1b0f3,0x30e532fb,0xb2542fd2,
  0x2b28b373,0x33cc2dd4,0xb285b18b,0x30a3b1c5,0x246a33fa,0xb3fba500,0x33962f42,0xad173321,0xadb1b3d0,0x337aaade,0xb3ffa99e,0x1f76b3e0,
  0xb0ee320d,0xb24db13c,0xac4b3398,0xb3b5ad0b,0x304ab289,0x32c1309e,0x2985b3ce,0x33e12b0f,0xaf3732f4,0xb324afe8,0xa4ce33f0,0xb3faa7ef,
  0x2dc8b34f,0x33762e82,0x9de4b3ff,0x33ff1ead,0xb1c931cd,0xb186b182,0xb3762e82,0xadc8b34f,0x324db13c,0x30ee320d,0x33b5ad0b,0x2c4b3398,
  0xb2c1309e,0xb04ab289,0xb3e12b0f,0xa985b3ce,0x3324afe8,0x2f3732f4,0x33faa7ef,0x24ce33f0,0xb285318b,0xb0a3b1c5,0xb2c7ae6b,0x3040b354,
  0x3396af42,0x2d173321,0x31413133,0xb2093215,0xb3ff299e,0x9f76b3e0,0xae8db2bd,0x334cb050,0x33b8278b,0xac3233f2,0x281033b3,0xb3ef2c57,
  0xb31e3146,0xaf4eb204,0xa533b394,0x33f9ad23,0x3400ab40,0x9c5233cb,0xae5f33e4,0xb357a93b,0xb2feac26,0x2fc8b3ba,0x3245b258,0x30f830e0,
  0x30553179,0xb2ba31d6,0xb3df2e99,0xa9b6b34a,0xb39230fd,0xad2fb241,0x3200b301,0x314a2fbd,0x337f1b11,0xad993400,0xb3ff2deb,0xa084b36f,
  0xb005b129,0x32ebb21d,0x325c2cdb,0xb0db339f,0xa92233de,0xb3e529cf,0xab59b2b6,0x33c9b05a,0xb3dd30b2,0xa9e8b27a,0x33d4ab71,0xaa9433c8,
  0x32212c0e,0xb12433bd,0xaf64b0d6,0x3318b260,0x197fb345,0x3400aeaf,0xae4833fe,0xb35c20e8,0xb23d3332,0xb102aeff,0x33aeb14f,0x2c7b31fc,
  0xb3fe3065,0xa14db2b0,0x2ebb307f,0xb342329e,0x300f2fa6,0xb2e53307,0x30d1b3f5,0x326426c3,0x302ab400,0x32d517db,0xb3e72e02,0x28f0b36a,
  0xb3fd2f6f,0x2343b316,0x2d46311f,0xb38e3225,0xb3f53015,0x2691b2e1,0xaf9b33eb,0xb30a288d,0x2a193166,0xb3da31e7,0x33d7aec6,0xaa63333f,
  0x3313b337,0x2f7a2ee8,0xa5fbb1f4,0x33f7b158,0xb1a1a8d7,0x31afb3e8,0xb36832d8,0xae0eb025,0xb3c22f85,0x2bd3b310,0xb3ea322d,0xa8a6b116,
  0xa8be32a9,0xb3e9306f,0x2bba3074,0xb3c332a5,0x33fdb111,0xa27a3231,0x3389b30d,0x2d5e2f90,0xa216b1aa,0x33feb1a6,0xaed2ae25,0x333db363,
  0xb3652edd,0x2e1ab33a,0xb1aa227a,0x31a6b3fd,0xaf853387,0xb3102d6a,0xb22d33fe,0xb116a216,0x32a9abd3,0xb06f33c2,0x307428a6,0xb2a533ea,
  0x3111b3e9,0x3231a8be,0x330db3c3,0x2f902bba,0xb2e12e31,0x3015b360,0x288db1a1,0x33ebb1af,0xb1e733f5,0xb1662691,0xb33f2f9b,0x2ec6b30a,
  0x2ee82a19,0xb33733da,0xb15833d7,0xb1f42a63,0x33e8b313,0x28d72f7a,0x302525fb,0xb2d833f7,0xb2392d81,0x3107b383,0x3307b3fe,0x2fa6214d,
  0xb35e33ec,0xae3ca874,0x97dbb00f,0x3400b2e5,0xa5c930b7,0xb3f83276,0xb316302a,0x2f6fb2d5,0x32b0aef4,0xb0653335,0xb29e33fd,0xb07f2343,
  0xb1702ccf,0x31dfb3a1,0x3345b124,0xaeaf3221,0xb3fc336c,0xa3a7adf7,0x3332b400,0x2eff997f,0xb0b23304,0xb27a2fb2,0x2b71b102,0x33c8b23d,
  0x2c0e29e8,0xb3bd33dd,0xb0d62a94,0x3260b3d4,0xb0892c1a,0x3297b3bc,0x2aad2842,0xb3d333ee,0xb3b0327e,0x2c6fb0ad,0x3241b035,0xb0fd32ce,
  0xb35933fc,0xae542406,0x3400b392,0x1b112d2f,0xaf5931da,0xb31b3174,0x321db37f,0x3129ad99,0xaf152ac6,0x332cb3d2,0xb1463293,0xb204308e,
  0xb281312e,0x30a8b219,0xab402f4e,0xb3cb331e,0xb3ef3371,0x2829addf,0x2c269c52,0xb3ba3400,0xb37c33f2,0xada52759,0x3179afc8,0xb1d632fe,
  0xacf32953,0x339cb3e3,0xb3fa33cc,0x2500ab28,0xb0942f21,0x3290b32a,0xb3d033fb,0xaade246a,0xb249317d,0x30f3b1d2,0xb2fb337a,0xafd22db1,
  0xb37332f1,0x2dd4aff3,0xb18b3254,0xb1c530e5,0xa96c27bd,0x33e2b3f1,0xb0452fdd,0x32c4b2f7,0xac3e2af7,0x33b7b3cf,0xb0ea3099,0x3250b28c,
  0xadbc2cff,0x3378b39a,0xb1823137,0x31cdb211,0xaf2c2e76,0x3327b352,0xb20d31c9,0x313cb186,0x313c3186,0xb20db1c9,0x2d0b2dc8,0xb398b376,
  0x309e30ee,0xb289b24d,0x2b0f2c4b,0xb3ceb3b5,0x2fe8304a,0xb2f4b2c1,0x27ef2985,0xb3f0b3e1,0x2e822f37,0xb34fb324,0x1ead24ce,0xb3ffb3fa,
  0xb2bdb209,0xb050b141,0xb290b32a,0x30942f21,0xb3b3b34c,0xac57ae8d,0xb0f3b1d2,0x3249317d,0xb400b3ef,0x1d1ba810,0xadd4aff3,0x337332f1,
  0xb39cb3e3,0x2cf32953,0xa500ab28,0x33fa33cc,0xae99b0f8,0x334a3245,0x33ff33b2,0x201f2c63,0x2438a9b6,0x33fc33df,0x332c33d2,0xaf15aac6,
  0x303a2ce7,0x32cb339e,0x30a83219,0xb281b12e,0x32ee31c0,0x2ffe3190,0x28292ddf,0xb3efb371,0x33b0327e,0x2c6f30ad,0xb241b035,0xb0fdb2ce,
  0x335933fc,0xae54a406,0xb400b392,0x1b11ad2f,0x2f5931da,0xb31bb174,0xb21db37f,0x31292d99,0xaaad2842,0xb3d3b3ee,0xa9cfb005,0x33de32eb,
  0x285b305f,0xb3edb2b3,0x2c0ea9e8,0x33bd33dd,0xb170accf,0xb1dfb3a1,0x33453124,0x2eaf3221,0xb3fcb36c,0x23a7adf7,0x33323400,0xaeff997f,
  0xb0b2b304,0x327a2fb2,0x2b713102,0xb3c8b23d,0xb400b2e5,0x17dbb00f,0x2e023264,0xb36ab0d1,0xaf6fb2d5,0x3316302a,0xb11fa8f0,0xb225b3e7,
  0x307f2343,0x329e33fd,0xb3d6b38e,0x2a7cad46,0x33f53342,0xa6c32ebb,0xac87b1e3,0x33ac316b,0x28d7af7a,0x33e83313,0xb2d8b3f7,0x3025a5fb,
  0x33eb31af,0x288d31a1,0x2bebae0e,0x33c03368,0x2ec6330a,0xb33faf9b,0x33fe3235,0x21b1310c,0xb1f4aa63,0xb158b3d7,0x2d5232a2,0xb38bb07a,
  0x33a7333d,0xacab2ed2,0x33f63162,0x262d31eb,0xaa4b301a,0xb3d8b2de,0x2a32326b,0xb3d9b0c7,0xb3f6b26f,0x265fb0c1,0xb3a9b020,0xac9fb2db,
  0x0e48b15d,0x340031f0,0xae1ab33a,0x33652edd,0xaed22e25,0xb33db363,0xb1eb0e48,0xb162b400,0xb2deb3a7,0x301aacab,0xb0c7b3f6,0x326b262d,
  0x30c1aa4b,0x326f33d8,0x32db2a32,0x302033d9,0x31f033f6,0xb15d265f,0x2edd33a9,0xb33aac9f,0xb2acb385,0x306aad76,0x2a19b166,0x33da31e7,
  0x3229a2de,0x311b33fd,0x33133337,0xaf7a2ee8,0x2e3133c5,0xb360aba2,0xb1a128d7,0xb1afb3e8,0xb3f5b015,0xa691b2e1,0xaf9bb3eb,0x330a288d,
  0x3154acc3,0x31f833a3,0x2ef433f8,0xb335a5c9,0x2d8133dc,0xb383aa01,0xb3feb065,0x214db2b0,0xb3ecb107,0x2874b239,0x300fafa6,0x32e53307,
  0x30b7ae3c,0x3276335e,0x302a3400,0xb2d517db,0x312433bd,0xb2212c0e,0xb318b260,0x2f64b0d6,0xb400aeaf,0x997fb345,0x335c20e8,0x2e4833fe,
  0x3102aeff,0x323d3332,0xac7b31fc,0xb3aeb14f,0x2a9433c8,0xb3d4ab71,0xb084b3e6,0x329ba909,0xb2ce2aad,0xb035b3d3,0x33e529cf,0x292233de,
  0x2d2fb241,0x339230fd,0xb14a2fbd,0xb200b301,0x2d993400,0xb37f1b11,0x2084b36f,0x33ff2deb,0xb2ebb21d,0x3005b129,0x30db339f,0xb25c2cdb,
  0xae5fb3e4,0x3357a93b,0xb190303a,0xb1c0b2cb,0x32453258,0xb0f830e0,0x2c63b2ee,0x33b22ffe,0xb3dfae99,0x29b6b34a,0x2ac633ff,0xb3d2a01f,
  0x339ea438,0x2ce733fc,0xb12eb32c,0x3219af15,0x33b8a78b,0x2c3233f2,0x2810b3b3,0x33ef2c57,0xb2c72e6b,0xb040b354,0x29533400,0xb3e31d1b,
  0x3141b133,0x32093215,0xaf21b39c,0x332aacf3,0xae8d32bd,0xb34cb050,0x317d3290,0xb1d23094,0x27bd33fb,0xb3f1249c,0x2fdd3327,0xb2f72f2c,
  0xaaf7b3e2,0x33cfa96c,0xb099b2c4,0x328cb045,0x2cff33b7,0xb39a2c3e,0x31373250,0xb21130ea,0xae76b378,0x3352adbc,0xb1c9b1cd,0x3186b182,
  0xb3ff1ead,0x1de4b3ff,0xb352adbc,0x2e76b378,0x33f1249c,0xa7bd33fb,0x32f72f2c,0xafdd3327,0xb3cfa96c,0x2af7b3e2,0xb28cb045,0x3099b2c4,
  0x339a2c3e,0xacff33b7,0x321130ea,0xb1373250,0x2953b400,0x33e31d1b,0x33ccadd4,0x2b283373,0xaf21339c,0xb32aacf3,0xb3fb2500,0x246ab3fa,
  0x317db290,0x31d23094,0x337a2ade,0xadb133d0,0xb2f130f3,0xaff3b249,0xb254afd2,0x30e5b2fb,0x339e2438,0xace733fc,0xb12e332c,0xb219af15,
  0xb190b03a,0x31c0b2cb,0x3371b0a8,0x2ddf3281,0x2c6332ee,0xb3b22ffe,0xb3f22829,0x2759b3ef,0x2ac6b3ff,0x33d2a01f,0x32932da5,0xb08e337c,
  0xaf0a33f3,0xb32fa727,0x2406b3b0,0x33fcac6f,0x3347b194,0x2ea431bc,0xb1743359,0xb1daae54,0xb3bc2565,0x2c1ab3f9,0x33eeaf59,0x2842331b,
  0x30ad3089,0xb27e3297,0xb2ceaaad,0x3035b3d3,0xb29ba909,0x3084b3e6,0x305f3030,0xb2b332d1,0x259732e8,0xb3f8300a,0x2ccfb3ed,0x33a1a85b,
  0x31b8b381,0x31992d8d,0xb36c31df,0xadf7b170,0xb3f42d3a,0x26f5b390,0x330423a7,0xafb233fc,0x316bb3d6,0x31e32a7c,0xb3832a01,0x2d81b3dc,
  0xb3bf2c87,0x2c02b3ac,0x28743239,0xb3ec3107,0x2b8931b3,0xb3c6319d,0x3276b35e,0x30b72e3c,0x31f8b3a3,0x31542cc3,0xb33525c9,0x2ef4b3f8,
  0x310c2beb,0xb23533c0,0x33abb267,0x2c9330cc,0x307ab3fe,0x32a2a1b1,0xb06aad76,0x32acb385,0xb3a52d52,0x2cb7b38b,0xb11b33fd,0xb229a2de,
  0x94b63273,0xb40030bc,0x3360aba2,0xae3133c5,0xb2de33a7,0xb01aacab,0xb0c733f6,0xb26b262d,0x30c12a4b,0xb26f33d8,0x32dbaa32,0xb02033d9,
  0x31f0b3f6,0x315d265f,0x2eddb3a9,0x333aac9f,0xb1eb8e48,0x3162b400,0xb3872e1a,0x2d6ab365,0xae25ad5e,0x3363b389,0x8e48b15d,0x3400b1f0,
  0xb3a7333d,0xacabaed2,0xb3f63162,0x262db1eb,0x2a4b301a,0xb3d832de,0xaa32326b,0xb3d930c7,0x33f6b26f,0x265f30c1,0x33a9b020,0xac9f32db,
  0x33c0b368,0x2beb2e0e,0x30cc94b6,0xb2673400,0x21b1b10c,0x33feb235,0x3385b3ab,0x2d762c93,0xb38b307a,0x2d52b2a2,0xa2deb06a,0x33fdb2ac,
  0xb0bc33a5,0xb2732cb7,0xb3c5311b,0x2ba2b229,0x26c32ebb,0xb3f53342,0xb3ac316b,0x2c87b1e3,0x336ab0d1,0xae023264,0xb19d33bf,0xb1b32c02,
  0x3225b3e7,0x311fa8f0,0x2cc32b89,0xb3a333c6,0xaa7cad46,0x33d6b38e,0x33dcb1f8,0xaa013154,0xb3fe3318,0x20e8af64,0x3381b3f8,0x2d8d2597,
  0xb14f335c,0xb1fc2e48,0x2d3ab199,0x3390b1b8,0x29092c7b,0xb3e633ae,0xb03026f5,0x32d1b3f4,0x32e8b084,0xb00a329b,0xb3ed32b3,0x285bb05f,
  0x29cfb005,0x33deb2eb,0xb05a325c,0xb2b630db,0xafbd2922,0x3301b3e5,0x27272b59,0xb3f333c9,0xb36f3200,0x2debb14a,0x31bcaf0a,0xb194332f,
  0xb39f33ff,0xacdba084,0x33f9b347,0xa5652ea4,0x3394b2ba,0xad233055,0xa438a9b6,0x33fcb3df,0x33e4b3f9,0x293b2533,0xb03a2ce7,0x32cbb39e,
  0x3258b357,0x30e0ae5f,0xb2ee31c0,0x2ffeb190,0x2e99b0f8,0x334ab245,0xb3ff33b2,0x201fac63,0xaf4230a3,0xb3213285,0x3133b040,0xb21532c7,
  0xa99e2d17,0xb3e03396,0x32bdb209,0xb0503141,0x278b1f76,0xb3f233ff,0x33b3b34c,0xac572e8d,0x2e6bac32,0xb35433b8,0x3400b3ef,0x1d1b2810,
  0xb289324d,0x309eb0ee,0xb3ce33b5,0x2b0fac4b,0xb2f432c1,0x2fe8b04a,0xb3f033e1,0x27efa985,0xb34f3324,0x2e82af37,0xb3ff33fa,0x1eada4ce,
  0xb3983376,0x2d0badc8,0xb3fb33ff,0xa49c1de4,0x351c35f6,0xac93a617,0xb8a3b93c,0x308d2a16,0x32f43448,0xb160afa5,0xb6a4b7fe,0x353a3389,
  0x2fa53160,0xb448b2f4,0xb389b53a,0x37fe36a4,0x26172c93,0xb5f6b51c,0xaa16b08d,0x393c38a3,0x34c3358c,0xac47a5b2,0xb85fb8f3,0x304229b1,
  0x327e33fd,0xb106af26,0xb63cb785,0x34e7330f,0x2f263106,0xb3fdb27e,0xb30fb4e7,0x3785363c,0x25b22c47,0xb58cb4c3,0xa9b1b042,0x38f3385f,
  0x346a3523,0xabf6a54d,0xb81ab8a8,0x2fef294d,0x3209336b,0xb0acaea7,0xb5d4b70a,0x34933294,0x2ea730ac,0xb36bb209,0xb294b493,0x370a35d4,
  0x254d2bf6,0xb523b46a,0xa94dafef,0x38a8381a,0x341334bc,0xab5fa4e9,0xb7a6b85a,0x2f5928e8,0x319432da,0xb052ae28,0xb56ab68d,0x343e3219,
  0x2e283052,0xb2dab194,0xb219b43e,0x368d356a,0x24e92b5f,0xb4bcb413,0xa8e8af59,0x385a37a6,0x33783456,0xaac8a484,0xb715b80a,0x2ec32884,
  0x3120324a,0xaff2ada9,0xb4ffb60e,0x33d3319e,0x2da92ff2,0xb24ab120,0xb19eb3d3,0x360e34ff,0x24842ac8,0xb456b378,0xa884aec3,0x380a3715,
  0x32cd33e3,0xaa31a420,0xb682b76f,0x2e2d281f,0x30ac31bb,0xaf3fad2a,0xb493b58d,0x33283122,0x2d2a2f3f,0xb1bbb0ac,0xb122b328,0x358d3493,
  0x24202a31,0xb3e3b2cd,0xa81fae2d,0x376f3682,0x3223331c,0xa999a376,0xb5ebb6c6,0x2d972776,0x3039312d,0xae8dacac,0xb426b50b,0x327c30a6,
  0x2cac2e8d,0xb12db039,0xb0a6b27c,0x350b3426,0x23762999,0xb31cb223,0xa776ad97,0x36c635eb,0x317a3257,0xa902a2ad,0xb552b61a,0x2d0026ad,
  0x2f8c309f,0xaddcac2e,0xb371b487,0x31cf3029,0x2c2e2ddc,0xb09faf8c,0xb029b1cf,0x34873371,0x22ad2902,0xb257b17a,0xa6adad00,0x361a3552,
  0x30d23194,0xa86ba1e4,0xb4b7b56a,0x2c6a25e4,0x2ea73012,0xad2aab5f,0xb294b402,0x31222f59,0x2b5f2d2a,0xb012aea7,0xaf59b122,0x34023294,
  0x21e4286b,0xb194b0d2,0xa5e4ac6a,0x356a34b7,0x302c30d2,0xa7a9a11b,0xb41ab4b7,0x2ba7251b,0x2dc22f0c,0xac79aa63,0xb1b6b2f7,0x30742e5f,
  0x2a632c79,0xaf0cadc2,0xae5fb074,0x32f731b6,0x211b27a9,0xb0d2b02c,0xa51baba7,0x34b7341a,0x2f0c3012,0xa67ba052,0xb2f7b402,0x2a7a2452,
  0x2cde2df5,0xab91a967,0xb0d7b1e8,0x2f8b2d65,0x29672b91,0xadf5acde,0xad65af8b,0x31e830d7,0x2052267b,0xb012af0c,0xa452aa7a,0x340232f7,
  0x2dc22ea7,0xa54d9f12,0xb1b6b294,0x294d2311,0x2bf62cde,0xaa31a86b,0xafefb0d7,0x2e2d2c6a,0x286b2a31,0xacdeabf6,0xac6aae2d,0x30d72fef,
  0x1f12254d,0xaea7adc2,0xa311a94d,0x329431b6,0x2c792d2a,0xa4209d7f,0xb074b122,0x281f217f,0x2a312b91,0xa8d0a6e0,0xae2daf8b,0x2cce2ade,
  0x26e028d0,0xab91aa31,0xaadeacce,0x2f8b2e2d,0x1d7f2420,0xad2aac79,0xa17fa81f,0x31223074,0x2a632b5f,0xa1e49bdb,0xae5faf59,0x25e41fdb,
  0x286b2967,0xa6e0a4e9,0xac6aad65,0x2ade28e8,0x24e926e0,0xa967a86b,0xa8e8aade,0x2d652c6a,0x1bdb21e4,0xab5faa63,0x9fdba5e4,0x2f592e5f,
  0x27a9286b,0x9f1298b6,0xaba7ac6a,0x23111cb6,0x254d267b,0xa420a1e4,0xa94daa7a,0x281f25e4,0x21e42420,0xa67ba54d,0xa5e4a81f,0x2a7a294d,
  0x18b61f12,0xa86ba7a9,0x9cb6a311,0x2c6a2ba7,0x211b21e4,0x98b69248,0xa51ba5e4,0x1cb61648,0x1f122052,0x9d7f9bdb,0xa311a452,0x217f1fdb,
  0x1bdb1d7f,0xa0529f12,0x9fdba17f,0x24522311,0x124818b6,0xa1e4a11b,0x96489cb6,0x25e4251b,0xa11ba1e4,0x18b61248,0x251b25e4,0x9cb69648,
  0x9f12a052,0x1d7f1bdb,0x23112452,0xa17f9fdb,0x9bdb9d7f,0x20521f12,0x1fdb217f,0xa452a311,0x924898b6,0x21e4211b,0x16481cb6,0xa5e4a51b,
  0xa7a9a86b,0x1f1218b6,0x2ba72c6a,0xa3119cb6,0xa54da67b,0x242021e4,0x294d2a7a,0xa81fa5e4,0xa1e4a420,0x267b254d,0x25e4281f,0xaa7aa94d,
  0x98b69f12,0x286b27a9,0x1cb62311,0xac6aaba7,0xaa63ab5f,0x21e41bdb,0x2e5f2f59,0xa5e49fdb,0xa86ba967,0x26e024e9,0x2c6a2d65,0xaadea8e8,
  0xa4e9a6e0,0x2967286b,0x28e82ade,0xad65ac6a,0x9bdba1e4,0x2b5f2a63,0x1fdb25e4,0xaf59ae5f,0xac79ad2a,0x24201d7f,0x30743122,0xa81fa17f,
  0xaa31ab91,0x28d026e0,0x2e2d2f8b,0xacceaade,0xa6e0a8d0,0x2b912a31,0x2ade2cce,0xaf8bae2d,0x9d7fa420,0x2d2a2c79,0x217f281f,0xb122b074,
  0xadc2aea7,0x254d1f12,0x31b63294,0xa94da311,0xabf6acde,0x2a31286b,0x2fef30d7,0xae2dac6a,0xa86baa31,0x2cde2bf6,0x2c6a2e2d,0xb0d7afef,
  0x9f12a54d,0x2ea72dc2,0x2311294d,0xb294b1b6,0xaf0cb012,0x267b2052,0x32f73402,0xaa7aa452,0xacdeadf5,0x2b912967,0x30d731e8,0xaf8bad65,
  0xa967ab91,0x2df52cde,0x2d652f8b,0xb1e8b0d7,0xa052a67b,0x30122f0c,0x24522a7a,0xb402b2f7,0xb02cb0d2,0x27a9211b,0x341a34b7,0xaba7a51b,
  0xadc2af0c,0x2c792a63,0x31b632f7,0xb074ae5f,0xaa63ac79,0x2f0c2dc2,0x2e5f3074,0xb2f7b1b6,0xa11ba7a9,0x30d2302c,0x251b2ba7,0xb4b7b41a,
  0xb0d2b194,0x286b21e4,0x34b7356a,0xac6aa5e4,0xaea7b012,0x2d2a2b5f,0x32943402,0xb122af59,0xab5fad2a,0x30122ea7,0x2f593122,0xb402b294,
  0xa1e4a86b,0x319430d2,0x25e42c6a,0xb56ab4b7,0xb17ab257,0x290222ad,0x3552361a,0xad00a6ad,0xaf8cb09f,0x2ddc2c2e,0x33713487,0xb1cfb029,
  0xac2eaddc,0x309f2f8c,0x302931cf,0xb487b371,0xa2ada902,0x3257317a,0x26ad2d00,0xb61ab552,0xb223b31c,0x29992376,0x35eb36c6,0xad97a776,
  0xb039b12d,0x2e8d2cac,0x3426350b,0xb27cb0a6,0xacacae8d,0x312d3039,0x30a6327c,0xb50bb426,0xa376a999,0x331c3223,0x27762d97,0xb6c6b5eb,
  0xb2cdb3e3,0x2a312420,0x3682376f,0xae2da81f,0xb0acb1bb,0x2f3f2d2a,0x3493358d,0xb328b122,0xad2aaf3f,0x31bb30ac,0x31223328,0xb58db493,
  0xa420aa31,0x33e332cd,0x281f2e2d,0xb76fb682,0xb378b456,0x2ac82484,0x3715380a,0xaec3a884,0xb120b24a,0x2ff22da9,0x34ff360e,0xb3d3b19e,
  0xada9aff2,0x324a3120,0x319e33d3,0xb60eb4ff,0xa484aac8,0x34563378,0x28842ec3,0xb80ab715,0xb413b4bc,0x2b5f24e9,0x37a6385a,0xaf59a8e8,
  0xb194b2da,0x30522e28,0x356a368d,0xb43eb219,0xae28b052,0x32da3194,0x3219343e,0xb68db56a,0xa4e9ab5f,0x34bc3413,0x28e82f59,0xb85ab7a6,
  0xb46ab523,0x2bf6254d,0x381a38a8,0xafefa94d,0xb209b36b,0x30ac2ea7,0x35d4370a,0xb493b294,0xaea7b0ac,0x336b3209,0x32943493,0xb70ab5d4,
  0xa54dabf6,0x3523346a,0x294d2fef,0xb8a8b81a,0xb4c3b58c,0x2c4725b2,0x385f38f3,0xb042a9b1,0xb27eb3fd,0x31062f26,0x363c3785,0xb4e7b30f,
  0xaf26b106,0x33fd327e,0x330f34e7,0xb785b63c,0xa5b2ac47,0x358c34c3,0x29b13042,0xb8f3b85f,0xb51cb5f6,0x2c932617,0x38a3393c,0xb08daa16,
  0xb2f4b448,0x31602fa5,0x36a437fe,0xb53ab389,0xafa5b160,0x344832f4,0x3389353a,0xb7feb6a4,0xa617ac93,0x35f6351c,0x2a16308d,0xb93cb8a3,
};
__device__ __align__(128) const uint32_t c_img[2560] = {
  0x326d31ed,0x333b32dd,0x33c33388,0x33fe33ea,0x33c331ed,0x31ed33c3,0xa8b22d64,0xb33bb0c4,0x33ea31ed,0xad64301d,0xb2ddb388,0x315fa8b2,
  0x32dd31ed,0xb3feabc6,0x326dad64,0xad64326d,0x30c431ed,0xaed7b2dd,0x2bc63388,0xa248b3ea,0x2bc631ed,0x315fb3c3,0xb3ea2d64,0x2ed730c4,
  0xa8b231ed,0x3388b01d,0x301db388,0xb1ed28b2,0xb01d31ed,0x22482bc6,0x30c4ad64,0x3388b26d,0x33ea33fe,0x338833c3,0x32dd333b,0x31ed326d,
  0xb2ddb3fe,0xa248b01d,0x326d2ed7,0x338833ea,0x30c433fe,0xb33babc6,0xabc6b33b,0x33fe30c4,0xabc6b3fe,0x31ed32dd,0xb3eaaed7,0x333ba8b2,
  0xa8b233fe,0x2d64b3c3,0xb01d333b,0x315fb26d,0x301db3fe,0xb3fe301d,0x30c42ed7,0x2d64b3ea,0xb26d33fe,0x2ed72bc6,0x33c3b33b,0xa248b0c4,
  0x33c3b3fe,0x315fb2dd,0x28b2aed7,0xaed728b2,0xb0c4b15f,0xaed7b01d,0xabc6ad64,0xa248a8b2,0xabc6b15f,0x315f2bc6,0x33ea3388,0x2ed7326d,
  0x28b2b15f,0x338832dd,0xb01d2d64,0xb1edb3ea,0x301db15f,0x224833c3,0xb0c4b388,0x338830c4,0x326db15f,0xb33b301d,0x33c3ad64,0xb3fe28b2,
  0x33c3b15f,0xb1edabc6,0xa8b23388,0x333bb26d,0x33eab15f,0x2d64b2dd,0xb2dd2d64,0xb15f33ea,0x32ddb15f,0x33feb3c3,0x326db388,0x2d64b0c4,
  0x28b22248,0x2d642bc6,0x301d2ed7,0x315f30c4,0xb01da248,0xb3feb2dd,0xb0c4b33b,0x2d64a8b2,0x326d2248,0x2ed733c3,0xb3c3aed7,0xa248b26d,
  0xb3c3a248,0x315fb01d,0xa8b2333b,0xaed7b3ea,0x33ea2248,0xb388abc6,0x32dd2ed7,0xb1edb0c4,0xb2dda248,0x224832dd,0x326db33b,0xb38828b2,
  0x30c42248,0x333bb3c3,0xabc6aed7,0xb3fe326d,0xabc6a248,0xb1ed301d,0xb3ea333b,0xb33b33ea,0xb26d31ed,0xb33b32dd,0xb3c33388,0xb3fe33ea,
  0xb3c331ed,0xb1ed33c3,0x28b22d64,0x333bb0c4,0xb3ea31ed,0x2d64301d,0x32ddb388,0xb15fa8b2,0xb2dd31ed,0x33feabc6,0xb26dad64,0x2d64326d,
  0xb0c431ed,0x2ed7b2dd,0xabc63388,0x2248b3ea,0xabc631ed,0xb15fb3c3,0x33ea2d64,0xaed730c4,0x28b231ed,0xb388b01d,0xb01db388,0x31ed28b2,
  0x301d31ed,0xa2482bc6,0xb0c4ad64,0xb388b26d,0xb3ea33fe,0xb38833c3,0xb2dd333b,0xb1ed326d,0x32ddb3fe,0x2248b01d,0xb26d2ed7,0xb38833ea,
  0xb0c433fe,0x333babc6,0x2bc6b33b,0xb3fe30c4,0x2bc6b3fe,0xb1ed32dd,0x33eaaed7,0xb33ba8b2,0x28b233fe,0xad64b3c3,0x301d333b,0xb15fb26d,
  0xb01db3fe,0x33fe301d,0xb0c42ed7,0xad64b3ea,0x326d33fe,0xaed72bc6,0xb3c3b33b,0x2248b0c4,0xb3c3b3fe,0xb15fb2dd,0xa8b2aed7,0x2ed728b2,
  0x30c4b15f,0x2ed7b01d,0x2bc6ad64,0x2248a8b2,0x2bc6b15f,0xb15f2bc6,0xb3ea3388,0xaed7326d,0xa8b2b15f,0xb38832dd,0x301d2d64,0x31edb3ea,
  0xb01db15f,0xa24833c3,0x30c4b388,0xb38830c4,0xb26db15f,0x333b301d,0xb3c3ad64,0x33fe28b2,0xb3c3b15f,0x31edabc6,0x28b23388,0xb33bb26d,
  0xb3eab15f,0xad64b2dd,0x32dd2d64,0x315f33ea,0xb2ddb15f,0xb3feb3c3,0xb26db388,0xad64b0c4,0xa8b22248,0xad642bc6,0xb01d2ed7,0xb15f30c4,
  0x301da248,0x33feb2dd,0x30c4b33b,0xad64a8b2,0xb26d2248,0xaed733c3,0x33c3aed7,0x2248b26d,0x33c3a248,0xb15fb01d,0x28b2333b,0x2ed7b3ea,
  0xb3ea2248,0x3388abc6,0xb2dd2ed7,0x31edb0c4,0x32dda248,0xa24832dd,0xb26db33b,0x338828b2,0xb0c42248,0xb33bb3c3,0x2bc6aed7,0x33fe326d,
  0x2bc6a248,0x31ed301d,0x33ea333b,0x333b33ea,0x30c4315f,0x2ed7301d,0x2bc62d64,0x224828b2,0x2bc6315f,0xb15fabc6,0xb3eab388,0xaed7b26d,
  0xa8b2315f,0xb388b2dd,0x301dad64,0x31ed33ea,0xb01d315f,0xa248b3c3,0x30c43388,0xb388b0c4,0xb26d315f,0x333bb01d,0xb3c32d64,0x33fea8b2,
  0xb3c3315f,0x31ed2bc6,0x28b2b388,0xb33b326d,0xb3ea315f,0xad6432dd,0x32ddad64,0x315fb3ea,0xb2dd315f,0xb3fe33c3,0xb26d3388,0xad6430c4,
  0xa8b2a248,0xad64abc6,0xb01daed7,0xb15fb0c4,0x301d2248,0x33fe32dd,0x30c4333b,0xad6428b2,0xb26da248,0xaed7b3c3,0x33c32ed7,0x2248326d,
  0x33c32248,0xb15f301d,0x28b2b33b,0x2ed733ea,0xb3eaa248,0x33882bc6,0xb2ddaed7,0x31ed30c4,0x32dd2248,0xa248b2dd,0xb26d333b,0x3388a8b2,
  0xb0c4a248,0xb33b33c3,0x2bc62ed7,0x33feb26d,0x2bc62248,0x31edb01d,0x33eab33b,0x333bb3ea,0x326d31ed,0x333b32dd,0x33c33388,0x33fe33ea,
  0x33c331ed,0x31ed33c3,0xa8b22d64,0xb33bb0c4,0x33ea31ed,0xad64301d,0xb2ddb388,0x315fa8b2,0x32dd31ed,0xb3feabc6,0x326dad64,0xad64326d,
  0x30c431ed,0xaed7b2dd,0x2bc63388,0xa248b3ea,0x2bc631ed,0x315fb3c3,0xb3ea2d64,0x2ed730c4,0xa8b231ed,0x3388b01d,0x301db388,0xb1ed28b2,
  0xb01d31ed,0x22482bc6,0x30c4ad64,0x3388b26d,0x33ea33fe,0x338833c3,0x32dd333b,0x31ed326d,0xb2ddb3fe,0xa248b01d,0x326d2ed7,0x338833ea,
  0x30c433fe,0xb33babc6,0xabc6b33b,0x33fe30c4,0xabc6b3fe,0x31ed32dd,0xb3eaaed7,0x333ba8b2,0xa8b233fe,0x2d64b3c3,0xb01d333b,0x315fb26d,
  0x301db3fe,0xb3fe301d,0x30c42ed7,0x2d64b3ea,0xb26d33fe,0x2ed72bc6,0x33c3b33b,0xa248b0c4,0x33c3b3fe,0x315fb2dd,0x28b2aed7,0xaed728b2,
  0xb0c4315f,0xaed7301d,0xabc62d64,0xa24828b2,0xabc6315f,0x315fabc6,0x33eab388,0x2ed7b26d,0x28b2315f,0x3388b2dd,0xb01dad64,0xb1ed33ea,
  0x301d315f,0x2248b3c3,0xb0c43388,0x3388b0c4,0x326d315f,0xb33bb01d,0x33c32d64,0xb3fea8b2,0x33c3315f,0xb1ed2bc6,0xa8b2b388,0x333b326d,
  0x33ea315f,0x2d6432dd,0xb2ddad64,0xb15fb3ea,0x32dd315f,0x33fe33c3,0x326d3388,0x2d6430c4,0x28b2a248,0x2d64abc6,0x301daed7,0x315fb0c4,
  0xb01d2248,0xb3fe32dd,0xb0c4333b,0x2d6428b2,0x326da248,0x2ed7b3c3,0xb3c32ed7,0xa248326d,0xb3c32248,0x315f301d,0xa8b2b33b,0xaed733ea,
  0x33eaa248,0xb3882bc6,0x32ddaed7,0xb1ed30c4,0xb2dd2248,0x2248b2dd,0x326d333b,0xb388a8b2,0x30c4a248,0x333b33c3,0xabc62ed7,0xb3feb26d,
  0xabc62248,0xb1edb01d,0xb3eab33b,0xb33bb3ea,0xb26d31ed,0xb33b32dd,0xb3c33388,0xb3fe33ea,0xb3c331ed,0xb1ed33c3,0x28b22d64,0x333bb0c4,
  0xb3ea31ed,0x2d64301d,0x32ddb388,0xb15fa8b2,0xb2dd31ed,0x33feabc6,0xb26dad64,0x2d64326d,0xb0c431ed,0x2ed7b2dd,0xabc63388,0x2248b3ea,
  0xabc631ed,0xb15fb3c3,0x33ea2d64,0xaed730c4,0x28b231ed,0xb388b01d,0xb01db388,0x31ed28b2,0x301d31ed,0xa2482bc6,0xb0c4ad64,0xb388b26d,
  0xb3ea33fe,0xb38833c3,0xb2dd333b,0xb1ed326d,0x32ddb3fe,0x2248b01d,0xb26d2ed7,0xb38833ea,0xb0c433fe,0x333babc6,0x2bc6b33b,0xb3fe30c4,
  0x2bc6b3fe,0xb1ed32dd,0x33eaaed7,0xb33ba8b2,0x28b233fe,0xad64b3c3,0x301d333b,0xb15fb26d,0xb01db3fe,0x33fe301d,0xb0c42ed7,0xad64b3ea,
  0x326d33fe,0xaed72bc6,0xb3c3b33b,0x2248b0c4,0xb3c3b3fe,0xb15fb2dd,0xa8b2aed7,0x2ed728b2,0x29ed29ed,0x29ed29ed,0x29ed29ed,0x29ed29ed,
  0x2bc32a6d,0x2add2bea,0x23c628c4,0xa81da0b2,0x2bc32add,0xa3c6281d,0xabc3aadd,0x23c6a81d,0x29ed2b3b,0xabfea564,0x295fa6d7,0x1a482b88,
  0x25642b88,0xa564ab88,0x25642b88,0xa564ab88,0xa0b22bc3,0x2a6daadd,0xabea23c6,0x28c4281d,0xa8c42bea,0x2a6da0b2,0x28c4abea,0xaa6d20b2,
  0xab3b2bfe,0xa564295f,0x26d79a48,0x2b88a9ed,0x29ed29ed,0x29ed29ed,0x29ed29ed,0x29ed29ed,0xabc3aa6d,0xaaddabea,0xa3c6a8c4,0x281d20b2,
  0x2bc32add,0xa3c6281d,0xabc3aadd,0x23c6a81d,0xa9edab3b,0x2bfe2564,0xa95f26d7,0x9a48ab88,0x25642b88,0xa564ab88,0x25642b88,0xa564ab88,
  0x20b2abc3,0xaa6d2add,0x2beaa3c6,0xa8c4a81d,0xa8c42bea,0x2a6da0b2,0x28c4abea,0xaa6d20b2,0x2b3babfe,0x2564a95f,0xa6d71a48,0xab8829ed,
  0x295f295f,0x295f295f,0x295f295f,0x295f295f,0x23c628c4,0xa81da0b2,0xabc3aa6d,0xaaddabea,0xa3c6281d,0xabc3aadd,0x23c6a81d,0x2bc32add,
  0xa95f26d7,0x9a48ab88,0x29ed2b3b,0xabfea564,0xab882564,0x2b88a564,0xab882564,0x2b88a564,0xabea23c6,0x28c4281d,0x20b2abc3,0xaa6d2add,
  0xaa6d20b2,0xa8c42bea,0x2a6da0b2,0x28c4abea,0xa6d71a48,0xab8829ed,0xab3b2bfe,0xa564295f,0x295f295f,0x295f295f,0x295f295f,0x295f295f,
  0xa3c6a8c4,0x281d20b2,0x2bc32a6d,0x2add2bea,0xa3c6281d,0xabc3aadd,0x23c6a81d,0x2bc32add,0x295fa6d7,0x1a482b88,0xa9edab3b,0x2bfe2564,
  0xab882564,0x2b88a564,0xab882564,0x2b88a564,0x2beaa3c6,0xa8c4a81d,0xa0b22bc3,0x2a6daadd,0xaa6d20b2,0xa8c42bea,0x2a6da0b2,0x28c4abea,
  0x26d79a48,0x2b88a9ed,0x2b3babfe,0x2564a95f,0xabfe2bfe,0xabfe2bfe,0xabfe2bfe,0xabfe2bfe,0xaadd2bea,0xa3c628c4,0x281da0b2,0x2bc3aa6d,
  0xa81d2bc3,0x2adda3c6,0x281dabc3,0xaadd23c6,0x9a482b88,0x29edab3b,0xabfe2564,0x295f26d7,0x26d72b3b,0xa6d7ab3b,0x26d72b3b,0xa6d7ab3b,
  0x2a6d2add,0xabeaa3c6,0x28c4a81d,0x20b22bc3,0x2bea2a6d,0xa0b228c4,0xabeaaa6d,0x20b2a8c4,0x2b8829ed,0x2b3b2bfe,0x2564295f,0xa6d79a48,
  0xabfe2bfe,0xabfe2bfe,0xabfe2bfe,0xabfe2bfe,0x2addabea,0x23c6a8c4,0xa81d20b2,0xabc32a6d,0xa81d2bc3,0x2adda3c6,0x281dabc3,0xaadd23c6,
  0x1a48ab88,0xa9ed2b3b,0x2bfea564,0xa95fa6d7,0x26d72b3b,0xa6d7ab3b,0x26d72b3b,0xa6d7ab3b,0xaa6daadd,0x2bea23c6,0xa8c4281d,0xa0b2abc3,
  0x2bea2a6d,0xa0b228c4,0xabeaaa6d,0x20b2a8c4,0xab88a9ed,0xab3babfe,0xa564a95f,0x26d71a48,0x1a489a48,0x1a489a48,0x1a489a48,0x1a489a48,
  0x281da0b2,0x2bc3aa6d,0x2addabea,0x23c6a8c4,0x2adda3c6,0x281dabc3,0xaadd23c6,0xa81d2bc3,0x2bfea564,0xa95fa6d7,0x9a482b88,0x29edab3b,
  0x2b3ba6d7,0xab3b26d7,0x2b3ba6d7,0xab3b26d7,0x28c4a81d,0x20b22bc3,0xaa6daadd,0x2bea23c6,0x20b2a8c4,0x2bea2a6d,0xa0b228c4,0xabeaaa6d,
  0xa564a95f,0x26d71a48,0x2b8829ed,0x2b3b2bfe,0x1a489a48,0x1a489a48,0x1a489a48,0x1a489a48,0xa81d20b2,0xabc32a6d,0xaadd2bea,0xa3c628c4,
  0x2adda3c6,0x281dabc3,0xaadd23c6,0xa81d2bc3,0xabfe2564,0x295f26d7,0x1a48ab88,0xa9ed2b3b,0x2b3ba6d7,0xab3b26d7,0x2b3ba6d7,0xab3b26d7,
  0xa8c4281d,0xa0b2abc3,0x2a6d2add,0xabeaa3c6,0x20b2a8c4,0x2bea2a6d,0xa0b228c4,0xabeaaa6d,0x2564295f,0xa6d79a48,0xab88a9ed,0xab3babfe,
  0xa95fa95f,0xa95fa95f,0xa95fa95f,0xa95fa95f,0xa3c6a8c4,0x281d20b2,0x2bc32a6d,0x2add2bea,0x23c6a81d,0x2bc32add,0xa3c6281d,0xabc3aadd,
  0x295fa6d7,0x1a482b88,0xa9edab3b,0x2bfe2564,0x2b88a564,0xab882564,0x2b88a564,0xab882564,0x2beaa3c6,0xa8c4a81d,0xa0b22bc3,0x2a6daadd,
  0x2a6da0b2,0x28c4abea,0xaa6d20b2,0xa8c42bea,0x26d79a48,0x2b88a9ed,0x2b3babfe,0x2564a95f,0xa95fa95f,0xa95fa95f,0xa95fa95f,0xa95fa95f,
  0x23c628c4,0xa81da0b2,0xabc3aa6d,0xaaddabea,0x23c6a81d,0x2bc32add,0xa3c6281d,0xabc3aadd,0xa95f26d7,0x9a48ab88,0x29ed2b3b,0xabfea564,
  0x2b88a564,0xab882564,0x2b88a564,0xab882564,0xabea23c6,0x28c4281d,0x20b2abc3,0xaa6d2add,0x2a6da0b2,0x28c4abea,0xaa6d20b2,0xa8c42bea,
  0xa6d71a48,0xab8829ed,0xab3b2bfe,0xa564295f,0x29ed29ed,0x29ed29ed,0x29ed29ed,0x29ed29ed,0x2bc32a6d,0x2add2bea,0x23c628c4,0xa81da0b2,
  0x2bc32add,0xa3c6281d,0xabc3aadd,0x23c6a81d,0x29ed2b3b,0xabfea564,0x295fa6d7,0x1a482b88,0x25642b88,0xa564ab88,0x25642b88,0xa564ab88,
  0xa0b22bc3,0x2a6daadd,0xabea23c6,0x28c4281d,0xa8c42bea,0x2a6da0b2,0x28c4abea,0xaa6d20b2,0xab3b2bfe,0xa564295f,0x26d79a48,0x2b88a9ed,
  0x29ed29ed,0x29ed29ed,0x29ed29ed,0x29ed29ed,0xabc3aa6d,0xaaddabea,0xa3c6a8c4,0x281d20b2,0x2bc32add,0xa3c6281d,0xabc3aadd,0x23c6a81d,
  0xa9edab3b,0x2bfe2564,0xa95f26d7,0x9a48ab88,0x25642b88,0xa564ab88,0x25642b88,0xa564ab88,0x20b2abc3,0xaa6d2add,0x2beaa3c6,0xa8c4a81d,
  0xa8c42bea,0x2a6da0b2,0x28c4abea,0xaa6d20b2,0x2b3babfe,0x2564a95f,0xa6d71a48,0xab8829ed,0x9a481a48,0x9a481a48,0x9a481a48,0x9a481a48,
  0xa81d20b2,0xabc32a6d,0xaadd2bea,0xa3c628c4,0xaadd23c6,0xa81d2bc3,0x2adda3c6,0x281dabc3,0xabfe2564,0x295f26d7,0x1a48ab88,0xa9ed2b3b,
  0xab3b26d7,0x2b3ba6d7,0xab3b26d7,0x2b3ba6d7,0xa8c4281d,0xa0b2abc3,0x2a6d2add,0xabeaa3c6,0xa0b228c4,0xabeaaa6d,0x20b2a8c4,0x2bea2a6d,
  0x2564295f,0xa6d79a48,0xab88a9ed,0xab3babfe,0x9a481a48,0x9a481a48,0x9a481a48,0x9a481a48,0x281da0b2,0x2bc3aa6d,0x2addabea,0x23c6a8c4,
  0xaadd23c6,0xa81d2bc3,0x2adda3c6,0x281dabc3,0x2bfea564,0xa95fa6d7,0x9a482b88,0x29edab3b,0xab3b26d7,0x2b3ba6d7,0xab3b26d7,0x2b3ba6d7,
  0x28c4a81d,0x20b22bc3,0xaa6daadd,0x2bea23c6,0xa0b228c4,0xabeaaa6d,0x20b2a8c4,0x2bea2a6d,0xa564a95f,0x26d71a48,0x2b8829ed,0x2b3b2bfe,
  0xabfe2bfe,0xabfe2bfe,0xabfe2bfe,0xabfe2bfe,0xaadd2bea,0xa3c628c4,0x281da0b2,0x2bc3aa6d,0xa81d2bc3,0x2adda3c6,0x281dabc3,0xaadd23c6,
  0x9a482b88,0x29edab3b,0xabfe2564,0x295f26d7,0x26d72b3b,0xa6d7ab3b,0x26d72b3b,0xa6d7ab3b,0x2a6d2add,0xabeaa3c6,0x28c4a81d,0x20b22bc3,
  0x2bea2a6d,0xa0b228c4,0xabeaaa6d,0x20b2a8c4,0x2b8829ed,0x2b3b2bfe,0x2564295f,0xa6d79a48,0xabfe2bfe,0xabfe2bfe,0xabfe2bfe,0xabfe2bfe,
  0x2addabea,0x23c6a8c4,0xa81d20b2,0xabc32a6d,0xa81d2bc3,0x2adda3c6,0x281dabc3,0xaadd23c6,0x1a48ab88,0xa9ed2b3b,0x2bfea564,0xa95fa6d7,
  0x26d72b3b,0xa6d7ab3b,0x26d72b3b,0xa6d7ab3b,0xaa6daadd,0x2bea23c6,0xa8c4281d,0xa0b2abc3,0x2bea2a6d,0xa0b228c4,0xabeaaa6d,0x20b2a8c4,
  0xab88a9ed,0xab3babfe,0xa564a95f,0x26d71a48,0x3bfb3bff,0x3be53bf2,0x3bbf3bd4,0x3b873ba5,0x3bd03bfb,0x3b013b7c,0x399d3a60,0x378538bc,
  0x35173b52,0xbbc9b7c8,0xb074ba9b,0x3bfe391b,0x319e3b27,0xbbf3b979,0x363cb80a,0x3a2d3bc5,0xba093986,0x3a7eb8f8,0xbae5385f,0x3b3db77a,
  0xbabd393c,0x3bb0b699,0xbc00305b,0x3ba730d7,0xbb2a35c8,0xb8353bb2,0x3a64b1e8,0x3962bbf7,0xba90350b,0xba413bff,0x3602340e,0x3bf6bad8,
  0xac6aa5e4,0xb122af59,0xb402b294,0xb56ab4b7,0xb2deac9c,0xb7bdb5a5,0xb9b3b8d6,0xbb10ba73,0xbb96b676,0xb359bafe,0x3bec3884,0x2a163a29,
  0xbbe0b72c,0x2f27b9d6,0x3b5e3ae8,0xb91633a2,0xb941b9c9,0x38ad3a45,0xb80fbab3,0x36d23b13,0xb850ba0d,0x346f3b4a,0x1fdbbbed,0xb4ab3be8,
  0x3721bb76,0xbace3463,0xb8d13bdd,0x39ebadfb,0x3894bb98,0xb8fd281f,0xbb6a3bbd,0x2e2d3825,0x3b3f3b65,0x3ae83b16,0x3a813ab6,0x3a0d3a49,
  0x3263356a,0xad972b43,0xb5dfb359,0xb8eeb7f3,0xa9b139aa,0xbbedba25,0x3340b889,0x3b983afb,0xbaa2aa16,0xb4cfbb8e,0x3c0038ad,0xb44b38e5,
  0xbb853625,0x3bbdb4c3,0xbbe432ad,0x3bfbaf8b,0xbaacb6d2,0x39243954,0xb65fbace,0x2fbd3bb8,0xb9661648,0xba603bf8,0x383a31cf,0x3b27bbb3,
  0x3219b9eb,0xbb1836f4,0xb9903be5,0x37dd3010,0xb6c6b61a,0xb80ab76f,0xb8a8b85a,0xb93cb8f3,0xbbd7bb87,0xbbf8bbfd,0xbb71bbc9,0xba4dbaf1,
  0xbbfeb9a6,0x305bb91f,0x3bcb3a97,0xb50b37d2,0xb87abbfe,0x3ba13546,0x24523a7e,0xbbb5ba54,0xb576bb63,0x340e3ba3,0xb13bbbd3,0x2c9c3bf2,
  0x386abb3d,0xba2139f8,0x3b57b835,0xbbf13432,0x39e7bc00,0xb8d6adc9,0xbacb3bde,0x372c3457,0x3bdab962,0x3764bb35,0xb9c03122,0xbaf73bef,
  0x398b39cd,0x38fd3946,0x386538b2,0x37853815,0xba85b9c9,0xbb92bb1e,0xbbfebbdd,0xbbc2bbf5,0xb66b3682,0xbb01bb94,0x387fb371,0x3a2d3beb,
  0xbac7bb76,0x3a00ad33,0x36bb3bd4,0xbbeab79b,0xbc0026ad,0x3bf32c38,0xbbd6b109,0x3ba733eb,0x3153bbff,0xb70a3b9e,0x396bba9b,0xbade390c,
  0xb5d4b5bc,0xbbb03b2c,0x32013830,0x3bf6ba67,0x3bccbb52,0x2c06b92e,0xbb83385f,0xb8c73bab,0xb9c5b982,0xba41ba04,0xbab0ba7a,0xbb10bae1,
  0xb8a3b986,0xb52fb74e,0xa94db1e8,0x33d32e91,0xbb54bb4f,0x37bdb523,0x3a9e3bc8,0xb916308d,0x3840b5c8,0x394a3bf9,0xbb42b294,0xb0a6bb0a,
  0x251bbbff,0xaf273bfc,0x327cbbe6,0xb4ab3bc0,0x3be325e4,0xbb2fb4e7,0x39e33884,0xb81aba35,0x3b73bb78,0xb46fb715,0xbbdc3ad1,0x2e2d38cc,
  0x33283676,0x3bfcba19,0x3581bab3,0xba6b3493,0x363136dd,0x34cf3581,0x32c6341a,0x2fbd3153,0xbae1bb65,0xb970ba39,0xb715b889,0xb16cb4f3,
  0xb9a12a7a,0xb924bbfe,0x3a933042,0x37dd3bcc,0x308db9aa,0x3b453b07,0xb94632ad,0xb845bbfa,0xbb68b55e,0x3b1836bb,0xbabab805,0x3a4d38a3,
  0x3bc0b625,0xbbfe2ec3,0x3b9431cf,0xba89b742,0x9cb6b95d,0xbbf8396b,0xb1b63a5c,0x3bb5b840,0x38cc9648,0x3b81bbac,0xac38b85a,0xbbce3933,
  0xbb60bb3a,0xbba1bb83,0xbbd2bbbc,0xbbf1bbe3,0x3815361a,0x39df3907,0x3b2c3a97,0x3be23b9c,0xb9afbbfd,0x3a21294d,0x388e3bee,0xbaf7b328,
  0x3beb39a6,0xb6af37a6,0xba04bbd3,0x3ac42d00,0x360ebb89,0xb7643b42,0x3855baeb,0xb8ee3a85,0x33eb3b63,0x28e8bbf5,0xb5233bde,0x389ebb21,
  0x3c00b9f0,0x2d97b9e3,0xbbdf38db,0xb44b3ac7,0xba673c00,0x358d3487,0x3bfcbab6,0x330fba15,0x3b7a3bf1,0x394a3a93,0x33893764,0xb3d39cb6,
  0x3afb3be2,0x35eb3946,0xb4c328e8,0xbaa9b8cc,0x27763af7,0xbb2fbaba,0x3a76ad97,0x30a63b60,0xaf8b3ac4,0xb994bb94,0x3bf8358d,0xb8743815,
  0xbb4c38ee,0x3bfcb1b6,0xbad5b4cf,0x381a39af,0xbbb3389e,0x3b592c38,0xb76fb970,0xb24b3beb,0xb9d2344b,0xbb923bd2,0xb0f03924,0x3a6bb60e,
  0xb8f3330f,0xbc003b2c,0xb91f3b45,0x323233eb,0xb5b1afbd,0xba00b88e,0xbbc6bb18,0xbbc2bc00,0xb7d2b16c,0xbb6fba04,0xbba3bbfe,0xb86fba67,
  0xbbffb7dd,0x370ab855,0x38b73bf8,0xbbeab631,0xbbf2b845,0x39bcb523,0x2dc93b81,0xbaa5bae1,0xb68dba4d,0xac063bdf,0x382abba1,0xbade39a1,
  0xb457ba89,0xb6543bfc,0x3b16b9df,0xbbd8308d,0x397dbbb5,0xb52fb2c6,0xbbe73a21,0xb8c73b68,0x3a49bbce,0x2311b715,0xba2536af,0xbbd93bc0,
  0xb958b785,0xbb81ba9e,0xbbefbbf3,0xba89bb73,0xbbf7bbc2,0xb9b8bb42,0xaf59b70a,0x384a3328,0xbb8bba2d,0x39dfb27c,0x34263bb0,0xbbceb98b,
  0xb4b7bbea,0x3b6c39e3,0xbafe2c06,0x3185ba85,0xaadebba7,0xb6af3bdc,0x3a58ba41,0xbbe2366b,0x3a29bade,0xbc003581,0x3a45352f,0xb2f7bac7,
  0x3b37bbf6,0x28e8b865,0xbaee37bd,0xbac43c00,0x3b13b8c7,0x3b5cbbfe,0x3463b94a,0xb8993153,0xb9f4bb10,0xb58db87f,0x3029af27,0x389e35d4,
  0x2dfbb3d3,0x399936bb,0x3bf23b2f,0x3ac13bcc,0x3552b916,0x39703bd6,0xbbbab46f,0x330fb9c5,0x3ba530a6,0xb5f7396b,0xb7c8bbfc,0x3be138a3,
  0x3bfdb4ab,0xbb45b201,0x38e038fd,0xb16cbb54,0x391b381a,0xa17fbb83,0xb8f83b92,0x3bcfb840,0x36e82e2d,0x3bfebab0,0x37febb01,0xb845251b,
  0xb77a3a6b,0x3648294d,0x3bb2ba00,0x3a8cbbe3,0xb742b93c,0x2311b340,0x37a6340e,0x3aa93966,0x3b963a4d,0x3b7f3c00,0x380f3a21,0xb0be3219,
  0x3933b50b,0x35eb3be4,0xbbf5b8d6,0x3874b6c6,0x39413bb5,0xbbffb65f,0x38d1b764,0x33ba3bd7,0x3b9c2c9c,0xb994b83a,0x34873ae8,0x324bbbfe,
  0xb7213bf1,0x3b47b990,0xbbbf2d97,0x38c1387a,0x2d00372c,0x3b59b8a8,0x3a39bbed,0xb232b576,0xbbfb3af7,0xb9743b71,0x307434cf,0x3adbb86a,
  0x3b213a0d,0x3c003bcb,0x3b073bbd,0x386f39e7,0x351738ee,0xb599a452,0xbae5b924,0xbbe9bbda,0x3a153b98,0xbb6fb13b,0x2ec3ba60,0x3aa53b3f,
  0xba09344b,0xa884bb57,0x3a643b18,0xbbc3b263,0xb4f33bfb,0x39bcbacb,0xbbac380a,0x3bd8a9b1,0xbb2aafbd,0x36a439c0,0x3402bbf8,0xba6f3aa2,
  0xbbfa3b27,0xb6543a81,0x3907b05b,0x3bd9bb85,0x2c6ab7dd,0xb9da35df,0xbbec3ba1,0xb8203aac,0x3bf53b87,0x3b6c3bec,0x392e3a7e,0x32f73721,
  0xb9e7b785,0xbbfcbb5e,0xba81bbb0,0xb43eb894,0x379b3bfe,0xbc00b80f,0x374eb835,0x38993bfb,0xbb3fba2d,0x3b329fdb,0xb3403a41,0xb8eabbd0,
  0xb90c3b3d,0x3b5cb8d1,0xbbf93122,0x3ac13517,0x29b1bba7,0xb94f3b6a,0x3be4b7bd,0xbaf4b19e,0xbbab3962,0xb9993bbf,0x34e73359,0x3be1ba09,
  0x3b85bbf6,0x353ab99d,0xb83a2f27,0xbbf03abd,0x2e91356a,0xb5f7b074,0xba19b8ad,0xbbcfbb2a,0xb966bb10,0xaba7b63c,0x38a8346f,0x3bb73a90,
  0xbb0aaa16,0xa17fbae5,0x3b1e3ace,0xba8c2c6a,0x36c6b916,0x36ff3c00,0xbbcbb8fd,0x3a50b2de,0xba35b6d2,0x36483a64,0x2d33bbe5,0xb84a3b96,
  0x3bfeb4ab,0xb9fcb602,0x313b3b01,0x37e8bbe0,0x3493b9eb,0xb9b83402,0xbb9e3bc9,0xb1853941,0x35762e2d,0x3b90b9b3,0x3acbbbf3,0x2fefb850,
  0x3a543bcf,0x2884374e,0xb9f8b648,0xbbe9bbab,0x398b3bb7,0xb4db3340,0xbbdcb9fc,0xb911bb85,0xb4323a8c,0xb6a4bbf9,0x3b3539b8,0xbbc3ae91,
  0xb66b3a50,0xad65bbe4,0x38653b90,0xbb0db966,0xbbef384a,0x39da34e7,0x2b43bb6c,0xba6f3b0a,0xbc0037e8,0x3759383a,0x387fbbfc,0xbbf636c6,
  0xb7f33185,0xbb7f3a19,0xbb8e3c00,0xb8203a35,0xb5d42fef,0xba1d38a8,0xbbd63b32,0xbba93bfe,0xb8e5b2f7,0xbbffbb1e,0xb954bb5c,0x30beb493,
  0xb9c5b43e,0xbb9fbbcb,0xb201b94f,0x3a313576,0xbbb8b899,0x3b47ad33,0xb6f43999,0xb3babbf5,0xbb54b8ea,0x3bf9313b,0xbab0353a,0x3790b9e7,
  0xb010bac1,0xb9743b9e,0x3bfdb5f7,0xb8c1b79b,0x251bbaf4,0xbb1b3acb,0x3a9e2ba7,0x2e5fbb3f,0x3af1bbe1,0x3599b92e,0xb546a17f,0xbadb390c,
  0x3b73bbf0,0x3929ba81,0x327cb6ff,0xb49f29b1,0xb825baa9,0x353aaec3,0x3b7c3994,0x3af43bfa,0x360eb0be,0x3bf43a64,0x388e3b47,0xb7372c6a,
  0x38bcb874,0x2ba73bac,0xb979bb59,0x3bf03742,0x3c0033ba,0xbb043402,0x3855b974,0xacce3b96,0x3bc5b24b,0xb6ffb907,0xb6993c00,0x3bb7b933,
  0x363138c1,0x3902bbec,0xbbdf3599,0x34ff3941,0x30d73232,0x39fcb7a6,0x3bffbb6f,0x3a50bb9c,0xb9a13adb,0xb47b380f,0x32c62884,0x3937b721,
  0x3ad8386f,0x3b903bf5,0x35a539bc,0xb7e8ad00,0x3b683be9,0x2ef538d1,0xba93b6a4,0xbb24bbfb,0x3a733aa5,0xbbfcb487,0x39d6b654,0xafef3b21,
  0x1cb63bc3,0xb7b2bbbf,0x3aba39da,0xbbfab517,0xb3a23bd8,0x3b32ba39,0xbb4a2311,0x343e3a15,0xbb603a6f,0x3a3d3074,0x31b6bb7f,0xbb9a3a09,
  0xbbe83bd9,0xb94f3b07,0xa81f35eb,0x38eab4f3,0xb9af3820,0xbbae3ae5,0xbbd23bff,0xba113b2a,0x319e389e,0xb929b426,0xbc00bb45,0xb911bb37,
  0xbbffbac1,0xb805bafe,0x382a217f,0x3bfd3b13,0xbabd330f,0x34dbba58,0x36023bfe,0xbb0db9f4,0xb68dbbe1,0x3a5c3a45,0xbbe7b648,0x3b89adfb,
  0xba90b16c,0x2d653aee,0x39b3bb81,0xbbf63552,0x397dbbcf,0xbbbc3463,0x338939b8,0x39f0bba5,0x32deb845,0xb7593029,0xbb5e39df,0xbba93bfd,
  0x3b7aba8c,0x3beebbf2,0x3a76bb6c,0x36ddb91b,0xbbe0ba89,0xba1dbbba,0x1fdbb6af,0x3a3136e8,0xa776b84a,0x3aeb37c8,0x3ad53c00,0xaa7a377a,
  0xb850bbce,0x3b9f38e0,0xbb6a28e8,0x3790b958,0x3b4cb185,0xb8db38f8,0x30f0bb5c,0x355e3bf7,0x3894bbe2,0xbbf937fe,0x399d358d,0x2e5fbb8b,
  0x39d232f7,0x341abbb2,0xbbc63999,0x395d34b7,0x3bd0bac4,0x3b1bbbef,0x363cb970,0xb49faade,0xb5b13899,0x30422f59,0x38b7b5f7,0x3b3aba29,
  0x3219b3d3,0x3b0438b7,0x3b713bfc,0x34ff397d,0x36e83aa9,0xb8b2adc9,0xbbefbb59,0xb5bcba49,0x3bd730a6,0xb902382a,0xa452bb92,0x39373b7a,
  0xb9583874,0x3371bb16,0x34263c00,0xb982bafb,0x387a381a,0x347bbbe7,0xbb573a00,0x3b242776,0xbb8b324b,0x31093a25,0x3a58bb6f,0xbb4f2f8b,
  0xb86a3a6b,0x2ef53389,0x39c0b70a,0x3bfabb4c,0xaadeb232,0xb83034c3,0xbaee39bc,0xbbff3bb3,0x3bda3bc2,0x37b23a76,0xb5df2c06,0xbb9ab9d2,
  0xbb37b86f,0xba7abbf8,0x3029b654,0x3b7838f3,0x32633bea,0xba3dbad5,0x3c00352f,0xba1135b1,0xb9f4baa5,0x3bc8376f,0xbbba2311,0x39cdb7d2,
  0xbaa23ade,0x3baeb0f0,0xb65fb94a,0xb7373bff,0x3552bbd8,0xbbe6391f,0x38e035eb,0x3682bbf2,0xbaac38c7,0xbbf43bc6,0xb9903b2f,0xacce368d,
  0x3bfdbbd9,0x3ad1bba3,0x37feb994,0x26adb457,0x38a33b9a,0xb8dba452,0xbb83bbae,0x2a7ab86a,0x37423b78,0xbab6b426,0xb907bbe6,0x39aa2ade,
  0xb8403a11,0x341abb57,0x294d3bf4,0xb55ebbda,0xb93339cd,0x3889ba58,0xb7a63ad1,0x3625bb37,0xbbe33737,0x304239c0,0x3b42bb04,0xb95db263,
  0xbb9c3682,0xb2ad3aee,0x3bf5b8b2,0x1648b9f4,0xb3282cce,0xb80535df,0xb9e33902,0xbb3a3aa2,0xad0026ad,0xb1cf3029,0xb4873371,0xb61a3552,
  0xba85b4ff,0xba5cbc00,0x3581b47b,0x3bfd3aac,0xbb21b5bc,0xb85abbba,0x3a393109,0x39a63bfd,0xbac7b937,0x3bbc365f,0xbbfeaef5,0x3b89b219,
  0xba15b982,0x3a9738e0,0xbb07b830,0x3b6336e8,0x3153bb24,0xbbee3990,0x36bb37b2,0x39f0bbd7,0x34f3bb4f,0xbbd337fe,0xaec33a7a,0x3c00b958,
  0x3bccbbfa,0x3aebbb71,0x396bba3d,0x36ddb87a,0x3bfabbff,0x3bdebbef,0x3bacbbc8,0x3b65bb8b,0x3bc03911,0x38303b6a,0xb946ad65,0xbb4fbbd0,
  0x3a353bfd,0xb85f30f0,0xbb1ebbbc,0x35c8b5b1,0x38cc3b0d,0xba7ab99d,0x3b943759,0xbbffb19e,0xb4933b89,0x31e8bbc6,0xad333bee,0xa5e4bbff,
  0xb8153bf6,0x3bc8b63c,0xac38ba1d,0xbb783abd,0xbbf539f0,0x329438b7,0x3b9ebaeb,0xb676b68d,0xbbeb3ba9,0xbbe63c00,0xbb2c3b9f,0xb9cd3a90,
  0xb79b36dd,0xb884382a,0xb92e38db,0xb9c9397d,0x33eb3a31,0xbad1b602,0xba04bbf9,0x3682b2de,0xb90c2a7a,0xbab3bbe7,0x374eb41a,0x3b763b7a,
  0xba673790,0x38b2b9b3,0xb5233b1b,0x26adbbe0,0xbbabb55e,0x3bdd3389,0xbbf9b042,0x3bff2776,0xbae12e5f,0xb3713b5e,0x3bfcb929,0xb5bcb850,
  0xae91b95d,0xbbd43a76,0x34e73805,0x3b52bb4c,0x308db49f,0xb1091fdb,0xb71534db,0xb9823894,0x3b0abb3a,0x3a9bbad5,0x3a19ba5c,0x3986b9d2,
  0x2f8bb7e8,0x3bde3979,0x376f3b32,0xb9aab0d7,0x3bb83b24,0xb1223855,0xbbfdba3d,0xaa16b9a1,0x3bb3afef,0xbab63699,0x391fb94f,0xb6253ad8,
  0x30103bfa,0xb359bbdf,0x35463bae,0xb6d2bb68,0x38f3343e,0x3889bbff,0xbba3353a,0x96483a73,0xbaf13b9a,0x38ad32c6,0x39f8bbf4,0xb9eb9cb6,
  0xb7d238ea,0xb2ad35a5,0x2dc92ba7,0x361ab3a2,0xba543a11,0xbace3a93,0xbb353b04,0xbb873b60,0x3bf23af4,0x31cf39d6,0xbb16b6ff,0xb9a6bbe8,
  0xb4323737,0xbbe5baba,0x2b43b902,0x3bfe39af,0x34573bf0,0xb85abb4a,0x3a2539fc,0xbb63b825,0xbbef2cce,0x3bc9b1b6,0xbb8e347b,0x3b3db60e,
  0xba493bb7,0x3a97a81f,0x34c3bb90,0xbc0038bc,0xb7f3b4ff,0xba7e3bd2,0x39542ef5,0x3962bc00,0xbafb3a50,0xbbd33b7c,0xbbf83bfc,0xbb653bc5,
  0x38e5b937,0x3835b88e,0x36f4b7b2,0x356ab631,0xbb13bbe9,0x31e8b6f4,0x3bf239da,0x36763af1,0x3be83911,0x340e3ab0,0xbb7cb759,0xb72cbb73,
  0x2dfbbbc3,0x32943bfd,0xb7c8bb7f,0x39c93a54,0x38253b0d,0xb8d6ba9e,0x39793a1d,0xba0db98b,0x3ba5ba6f,0xb884b546,0xb8f83bff,0x3b76b432,
  0xb8bc3bf6,0x3ae8b27c,0x3699bb9f,0xbb98366b,0x391bb820,0x3ab3b9f8,0x3bb2bb47,0x3bffbbef,0xbbc53ba9,0xbbed3bdc,0xbbff3bf9,0xbbfb3c00,
  0x377ab0be,0x3bdd3b35,0x2f593974,0xbb52b7f3,0x30d73a31,0xbbbdb865,0xb5a5bb1b,0x3b2735d4,0x3bf733ba,0xbbd42b43,0x3afeb599,0xb98638e5,
  0xbad83790,0x3a60b87f,0xb9d63929,0x393cb9c5,0x34b738c1,0x3a9bbb8e,0xba45a884,0xb5c83bb8,0xba732e5f,0xb80a3bd6,0x3b4ab4db,0x350bbb54,
  0xba293adb,0xb85f3954,0xb46336a4,0x25e43010,0x33a2b49f,0x305bb201,0x281fad65,0xac9c251b,0x3f803f80,0x3f803f80,0x3f803f80,0x3f803f80,
  0x3f803f80,0x3f803f80,0x3f803f80,0x3f803f80,0x3f803f80,0x3f803f80,0x3f803f80,0x3f803f80,0x3f803f80,0x3f803f80,0x3f803f80,0x3f803f80,
  0x3f803f80,0x3f803f80,0x3f803f80,0x3f803f80,0x3f803f80,0x3f803f80,0x3f803f80,0x3f803f80,0x3f803f80,0x3f803f80,0x3f803f80,0x3f803f80,
  0x3f803f80,0x3f803f80,0x3f803f80,0x3f803f80,0x3f803f80,0x3f803f80,0x3f803f80,0x3f803f80,0x3f803f80,0x3f803f80,0x3f803f80,0x3f803f80,
  0x3f803f80,0x3f803f80,0x3f803f80,0x3f803f80,0x3f803f80,0x3f803f80,0x3f803f80,0x3f803f80,0x3f803f80,0x3f803f80,0x3f803f80,0x3f803f80,
  0x3f803f80,0x3f803f80,0x3f803f80,0x3f803f80,0x3f803f80,0x3f803f80,0x3f803f80,0x3f803f80,0x3f803f80,0x3f803f80,0x3f803f80,0x3f803f80,
  0x3f803f80,0x3f803f80,0x3f803f80,0x3f803f80,0x3f803f80,0x3f803f80,0x3f803f80,0x3f803f80,0x3f803f80,0x3f803f80,0x3f803f80,0x3f803f80,
  0x3f803f80,0x3f803f80,0x3f803f80,0x3f803f80,0x3f803f80,0x3f803f80,0x3f803f80,0x3f803f80,0x3f803f80,0x3f803f80,0x3f803f80,0x3f803f80,
  0x3f803f80,0x3f803f80,0x3f803f80,0x3f803f80,0x3f803f80,0x3f803f80,0x3f803f80,0x3f803f80,0x3f803f80,0x3f803f80,0x3f803f80,0x3f803f80,
  0x3f803f80,0x3f803f80,0x3f803f80,0x3f803f80,0x3f803f80,0x3f803f80,0x3f803f80,0x3f803f80,0x3f803f80,0x3f803f80,0x3f803f80,0x3f803f80,
  0x3f803f80,0x3f803f80,0x3f803f80,0x3f803f80,0x3f803f80,0x3f803f80,0x3f803f80,0x3f803f80,0x3f803f80,0x3f803f80,0x3f803f80,0x3f803f80,
  0x3f803f80,0x3f803f80,0x3f803f80,0x3f803f80,0x3f803f80,0x3f803f80,0x3f803f80,0x3f803f80,0x3f803f80,0x3f803f80,0x3f803f80,0x3f803f80,
  0x3f803f80,0x3f803f80,0x3f803f80,0x3f803f80,0x3f803f80,0x3f803f80,0x3f803f80,0x3f803f80,0x3f803f80,0x3f803f80,0x3f803f80,0x3f803f80,
  0x3f803f80,0x3f803f80,0x3f803f80,0x3f803f80,0x3f803f80,0x3f803f80,0x3f803f80,0x3f803f80,0x3f803f80,0x3f803f80,0x3f803f80,0x3f803f80,
  0x3f803f80,0x3f803f80,0x3f803f80,0x3f803f80,0x3f803f80,0x3f803f80,0x3f803f80,0x3f803f80,0x3f803f80,0x3f803f80,0x3f803f80,0x3f803f80,
  0x3f803f80,0x3f803f80,0x3f803f80,0x3f803f80,0x3f803f80,0x3f803f80,0x3f803f80,0x3f803f80,0x3f803f80,0x3f803f80,0x3f803f80,0x3f803f80,
  0x3f803f80,0x3f803f80,0x3f803f80,0x3f803f80,0x3f803f80,0x3f803f80,0x3f803f80,0x3f803f80,0x3f803f80,0x3f803f80,0x3f803f80,0x3f803f80,
  0x3f803f80,0x3f803f80,0x3f803f80,0x3f803f80,0x3f803f80,0x3f803f80,0x3f803f80,0x3f803f80,0x3f803f80,0x3f803f80,0x3f803f80,0x3f803f80,
  0x3f803f80,0x3f803f80,0x3f803f80,0x3f803f80,0x3f803f80,0x3f803f80,0x3f803f80,0x3f803f80,0x3f803f80,0x3f803f80,0x3f803f80,0x3f803f80,
  0x3f803f80,0x3f803f80,0x3f803f80,0x3f803f80,0x3f803f80,0x3f803f80,0x3f803f80,0x3f803f80,0x3f803f80,0x3f803f80,0x3f803f80,0x3f803f80,
  0x3f803f80,0x3f803f80,0x3f803f80,0x3f803f80,0x3f803f80,0x3f803f80,0x3f803f80,0x3f803f80,0x3f803f80,0x3f803f80,0x3f803f80,0x3f803f80,
  0x3f803f80,0x3f803f80,0x3f803f80,0x3f803f80,0x3f803f80,0x3f803f80,0x3f803f80,0x3f803f80,0x3f803f80,0x3f803f80,0x3f803f80,0x3f803f80,
  0x3f803f80,0x3f803f80,0x3f803f80,0x3f803f80,0x3f803f80,0x3f803f80,0x3f803f80,0x3f803f80,0x3f803f80,0x3f803f80,0x3f803f80,0x3f803f80,
  0x3f803f80,0x3f803f80,0x3f803f80,0x3f803f80,0x3f803f80,0x3f803f80,0x3f803f80,0x3f803f80,0x3f803f80,0x3f803f80,0x3f803f80,0x3f803f80,
  0x3f803f80,0x3f803f80,0x3f803f80,0x3f803f80,0x3f803f80,0x3f803f80,0x3f803f80,0x3f803f80,0x3f803f80,0x3f803f80,0x3f803f80,0x3f803f80,
  0x3f803f80,0x3f803f80,0x3f803f80,0x3f803f80,0x3f803f80,0x3f803f80,0x3f803f80,0x3f803f80,0x3f803f80,0x3f803f80,0x3f803f80,0x3f803f80,
  0x3f803f80,0x3f803f80,0x3f803f80,0x3f803f80,0x3f803f80,0x3f803f80,0x3f803f80,0x3f803f80,0x3f803f80,0x3f803f80,0x3f803f80,0x3f803f80,
  0x3f803f80,0x3f803f80,0x3f803f80,0x3f803f80,0x3f803f80,0x3f803f80,0x3f803f80,0x3f803f80,0x3f803f80,0x3f803f80,0x3f803f80,0x3f803f80,
  0x3f803f80,0x3f803f80,0x3f803f80,0x3f803f80,0x3f803f80,0x3f803f80,0x3f803f80,0x3f803f80,0x3f803f80,0x3f803f80,0x3f803f80,0x3f803f80,
  0x3f803f80,0x3f803f80,0x3f803f80,0x3f803f80,0x3f803f80,0x3f803f80,0x3f803f80,0x3f803f80,0x3f803f80,0x3f803f80,0x3f803f80,0x3f803f80,
  0x3f803f80,0x3f803f80,0x3f803f80,0x3f803f80,0x3f803f80,0x3f803f80,0x3f803f80,0x3f803f80,0x3f803f80,0x3f803f80,0x3f803f80,0x3f803f80,
  0x3f803f80,0x3f803f80,0x3f803f80,0x3f803f80,0x3f803f80,0x3f803f80,0x3f803f80,0x3f803f80,0x3f803f80,0x3f803f80,0x3f803f80,0x3f803f80,
  0x3f803f80,0x3f803f80,0x3f803f80,0x3f803f80,0x3f803f80,0x3f803f80,0x3f803f80,0x3f803f80,0x3f803f80,0x3f803f80,0x3f803f80,0x3f803f80,
  0x3f803f80,0x3f803f80,0x3f803f80,0x3f803f80,0x3f803f80,0x3f803f80,0x3f803f80,0x3f803f80,0x3f803f80,0x3f803f80,0x3f803f80,0x3f803f80,
  0x3f803f80,0x3f803f80,0x3f803f80,0x3f803f80,0x3f803f80,0x3f803f80,0x3f803f80,0x3f803f80,0x3f803f80,0x3f803f80,0x3f803f80,0x3f803f80,
  0x3f803f80,0x3f803f80,0x3f803f80,0x3f803f80,0x3f803f80,0x3f803f80,0x3f803f80,0x3f803f80,0x3f803f80,0x3f803f80,0x3f803f80,0x3f803f80,
  0x3f803f80,0x3f803f80,0x3f803f80,0x3f803f80,0x3f803f80,0x3f803f80,0x3f803f80,0x3f803f80,0x3f803f80,0x3f803f80,0x3f803f80,0x3f803f80,
  0x3f803f80,0x3f803f80,0x3f803f80,0x3f803f80,0x3f803f80,0x3f803f80,0x3f803f80,0x3f803f80,0x3f803f80,0x3f803f80,0x3f803f80,0x3f803f80,
  0x3f803f80,0x3f803f80,0x3f803f80,0x3f803f80,0x3f803f80,0x3f803f80,0x3f803f80,0x3f803f80,0x3f803f80,0x3f803f80,0x3f803f80,0x3f803f80,
  0x3f803f80,0x3f803f80,0x3f803f80,0x3f803f80,0x3f803f80,0x3f803f80,0x3f803f80,0x3f803f80,0x3f803f80,0x3f803f80,0x3f803f80,0x3f803f80,
  0x3f803f80,0x3f803f80,0x3f803f80,0x3f803f80,0x3f803f80,0x3f803f80,0x3f803f80,0x3f803f80,0x3f803f80,0x3f803f80,0x3f803f80,0x3f803f80,
  0x3f803f80,0x3f803f80,0x3f803f80,0x3f803f80,0x3f803f80,0x3f803f80,0x3f803f80,0x3f803f80,0x3f803f80,0x3f803f80,0x3f803f80,0x3f803f80,
  0x3f803f80,0x3f803f80,0x3f803f80,0x3f803f80,0x3f803f80,0x3f803f80,0x3f803f80,0x3f803f80,0x3f803f80,0x3f803f80,0x3f803f80,0x3f803f80,
  0x3f803f80,0x3f803f80,0x3f803f80,0x3f803f80,
};

__device__ __align__(128) float    g_part[16][8][2176];
__device__ __align__(128) float    g_kv[16][2176];
constexpr int OBLK = 16 * 1024 + 32;
__device__ __align__(128) uint4    g_o[16 * OBLK];
#define GSTAMP(role, i) do {} while (0)
#define STAMP(role, i) do {} while (0)
#define PDUMP(role) do {} while (0)
#define PROF_SMEM 0

constexpr int STAGE_BYTES = 57344;
constexpr int OFF_H = 4 * 16384, OFF_VP = 9 * 16384, OFF_SPARE = 10 * 16384;
constexpr int OFF_XT = 172032, XT_STRIDE = 4112;
constexpr int OFF_BAR = 204928, OFF_EPOCH = OFF_BAR + 640, OFF_EX = OFF_BAR + 656, OFF_D = OFF_BAR + 672, OFF_SCALE = OFF_BAR + 704;
constexpr int OFF_F2F = 205824, OFF_F2I = 207872, OFF_F4 = 209920, OFF_ONES = 214016, OFF_KVB = 214016;
constexpr int OFF_STG = 219136, STG_STRIDE = 4352, SMEM_TOTAL = 232192 + PROF_SMEM;
enum { B_FULL1 = 0, B_EMPTY1 = 3, B_Q = 6, B_ODONE1 = 7, B_O1RDY = 8, B_H = 9, B_XRAW = 10, B_XT = 11, B_KV = 12, B_Y = 13,  B_AFREE = 15,
       B_STG = 18, B_ODONE = 24, B_XFREE = 25, B_FULL2 = 33, B_CONS2 = 49, B_SFREE = 14, B_KV1 = 61, B_OLOC = 60, B_PKRDY = 62, B_PKFREE = 64, B_H2 = 65, B_G1DONE = 66, B_COUNT = 67, B_FIRST = 67 };
constexpr uint64_t SLOT_A = 0x6859468594685948ull, SLOT_B = 0x7103271032710326ull;
constexpr int NPRE = 6, BEARLY = 3;
__host__ __device__ constexpr int bar_count(int i) {
  return i < B_EMPTY1 ? 1 : i < B_Q ? 4 : i == B_XT ? 4 : i == B_H ? 4 : (i == B_SFREE || i == B_G1DONE) ? 2 : i >= B_PKFREE ? 4 : i >= B_PKRDY ? 8 : i == B_Y ? 9
       : (i >= B_AFREE && i < B_STG) ? 16 : (i == B_ODONE || i == B_ODONE1) ? 8 : (i >= B_XFREE && i < B_FULL2) ? 4
       : i == B_KV1 ? 1 : i == B_OLOC ? 2 : i >= B_CONS2 ? 4 : (i >= B_FULL2 && i < B_FULL2 + NPRE) ? 2 : 1;
}
__host__ __device__ constexpr uint64_t bar_counts(int r) {
  uint64_t v = 0;
  for (int w = 0; w < 11; w++) v |= (uint64_t)(bar_count(1 + 11 * r + w) - 1) << (4 * w);
  return v;
}
constexpr uint32_t SW128 = 64 | (1u << 30);
constexpr int SPIN_LIMIT = 1 << 22;
#define SPLIT0 2
#define OLOC 1
#define G2E 1
#define G2P 1
#define RC 200
#define PFD 3
#define PD1 700
#define PD2 450
#define QPF 6
#define BPACE 250
#define OCH 3
#define O1D 0
#define HOLD2 12
#define D1 100
#define TRICK 3
#define HSTART 1500
#define PACE 800

__device__ __forceinline__ uint32_t smem_u32(const void* p) { return (uint32_t)__cvta_generic_to_shared(p); }
__device__ __forceinline__ void wg_fence() { asm volatile("wgmma.fence.sync.aligned;" ::: "memory"); }
__device__ __forceinline__ void wg_commit() { asm volatile("wgmma.commit_group.sync.aligned;" ::: "memory"); }
template <int N> __device__ __forceinline__ void wg_wait() { asm volatile("wgmma.wait_group.sync.aligned %0;" ::"n"(N) : "memory"); }
template <int N> __device__ __forceinline__ void keep(float (&d)[N]) {
#pragma unroll
  for (int i = 0; i < N; i++) asm volatile("" : "+f"(d[i])::"memory");
}
__device__ __forceinline__ void mbar_init(uint32_t bar, int cnt) { asm volatile("mbarrier.init.shared::cta.b64 [%0], %1;" ::"r"(bar), "r"(cnt)); }
__device__ __forceinline__ void mbar_expect(uint32_t bar, int bytes) { asm volatile("mbarrier.arrive.expect_tx.shared::cta.b64 _, [%0], %1;" ::"r"(bar), "r"(bytes) : "memory"); }
__device__ __forceinline__ void mbar_arrive(uint32_t bar) { asm volatile("mbarrier.arrive.shared::cta.b64 _, [%0];" ::"r"(bar) : "memory"); }
__device__ __forceinline__ void mbar_arrive_cl(uint32_t bar, uint32_t cta) {
  asm volatile("{\n.reg .b32 r;\nmapa.shared::cluster.u32 r, %0, %1;\nmbarrier.arrive.shared::cluster.b64 _, [r];\n}\n" ::"r"(bar), "r"(cta) : "memory");
}
__device__ __forceinline__ void mbar_wait(uint32_t bar, uint32_t parity) {
  asm volatile("{\n.reg .pred p;\n.reg .u32 n;\nmov.u32 n, 0;\n"
               "W_%=:\nmbarrier.try_wait.parity.shared::cta.b64 p, [%0], %1;\n@p bra D_%=;\n"
               "add.u32 n, n, 1;\nsetp.lt.u32 p, n, %2;\n@p bra W_%=;\ntrap;\nD_%=:\n}\n" ::"r"(bar), "r"(parity), "n"(SPIN_LIMIT) : "memory");
}
__device__ __forceinline__ void fence_async() { asm volatile("fence.proxy.async.shared::cta;" ::: "memory"); }
__device__ __forceinline__ void bar_sync(int id) { asm volatile("bar.sync %0, 128;" ::"r"(id) : "memory"); }
__device__ __forceinline__ void tma2d(uint32_t dst, const CUtensorMap* m, int c0, int c1, uint32_t bar) {
  asm volatile("cp.async.bulk.tensor.2d.shared::cluster.global.mbarrier::complete_tx::bytes [%0], [%1, {%3, %4}], [%2];"
               ::"r"(dst), "l"(m), "r"(bar), "r"(c0), "r"(c1) : "memory");
}
__device__ __forceinline__ void tma2d_mc(uint32_t dst, const CUtensorMap* m, int c0, int c1, uint32_t bar) {
  asm volatile("cp.async.bulk.tensor.2d.shared::cluster.global.mbarrier::complete_tx::bytes.multicast::cluster [%0], [%1, {%3, %4}], [%2], %5;"
               ::"r"(dst), "l"(m), "r"(bar), "r"(c0), "r"(c1), "h"((uint16_t)3) : "memory");
}
__device__ __forceinline__ void tma3d(uint32_t dst, const CUtensorMap* m, int c0, int c1, int c2, uint32_t bar) {
  asm volatile("cp.async.bulk.tensor.3d.shared::cluster.global.mbarrier::complete_tx::bytes [%0], [%1, {%3, %4, %5}], [%2];"
               ::"r"(dst), "l"(m), "r"(bar), "r"(c0), "r"(c1), "r"(c2) : "memory");
}
__device__ __forceinline__ void tma4d(uint32_t dst, const CUtensorMap* m, int c0, int c1, int c2, int c3, uint32_t bar) {
  asm volatile("cp.async.bulk.tensor.4d.shared::cluster.global.mbarrier::complete_tx::bytes [%0], [%1, {%3, %4, %5, %6}], [%2];"
               ::"r"(dst), "l"(m), "r"(bar), "r"(c0), "r"(c1), "r"(c2), "r"(c3) : "memory");
}
__device__ __forceinline__ void bulk_ld(uint32_t dst, const void* src, int bytes, uint32_t bar) {
  asm volatile("cp.async.bulk.shared::cluster.global.mbarrier::complete_tx::bytes [%0], [%1], %2, [%3];" ::"r"(dst), "l"(src), "r"(bytes), "r"(bar) : "memory");
}
__device__ __forceinline__ void bulk_ld_mc(uint32_t dst, const void* src, int bytes, uint32_t bar) {
  asm volatile("cp.async.bulk.shared::cluster.global.mbarrier::complete_tx::bytes.multicast::cluster [%0], [%1], %2, [%3], %4;"
               ::"r"(dst), "l"(src), "r"(bytes), "r"(bar), "h"((uint16_t)3) : "memory");
}
__device__ __forceinline__ void tma2d_st(const CUtensorMap* m, uint32_t src, int c0, int c1) {
  asm volatile("cp.async.bulk.tensor.2d.global.shared::cta.bulk_group [%0, {%2, %3}], [%1];" ::"l"(m), "r"(src), "r"(c0), "r"(c1) : "memory");
}
__device__ __forceinline__ void ldsm4(uint32_t (&r)[4], uint32_t a) {
  asm volatile("ldmatrix.sync.aligned.m8n8.x4.shared.b16 {%0,%1,%2,%3}, [%4];" : "=r"(r[0]), "=r"(r[1]), "=r"(r[2]), "=r"(r[3]) : "r"(a) : "memory");
}
__device__ __forceinline__ void ldsm4t(uint32_t (&r)[4], uint32_t a) {
  asm volatile("ldmatrix.sync.aligned.m8n8.x4.trans.shared.b16 {%0,%1,%2,%3}, [%4];" : "=r"(r[0]), "=r"(r[1]), "=r"(r[2]), "=r"(r[3]) : "r"(a) : "memory");
}
__device__ __forceinline__ void stsm4(uint32_t a, uint32_t r0, uint32_t r1, uint32_t r2, uint32_t r3) {
  asm volatile("stmatrix.sync.aligned.m8n8.x4.shared.b16 [%0], {%1,%2,%3,%4};" ::"r"(a), "r"(r0), "r"(r1), "r"(r2), "r"(r3) : "memory");
}
__device__ __forceinline__ uint32_t pk2(float lo, float hi) { uint32_t r; asm("cvt.rn.bf16x2.f32 %0, %1, %2;" : "=r"(r) : "f"(hi), "f"(lo)); return r; }
__device__ __forceinline__ uint32_t hmul(uint32_t a, uint32_t b) { uint32_t r; asm("mul.rn.bf16x2 %0, %1, %2;" : "=r"(r) : "r"(a), "r"(b)); return r; }
__device__ __forceinline__ uint32_t hadd(uint32_t a, uint32_t b) { uint32_t r; asm("add.rn.bf16x2 %0, %1, %2;" : "=r"(r) : "r"(a), "r"(b)); return r; }
__device__ __forceinline__ uint32_t hmin(uint32_t a, uint32_t b) { uint32_t r; asm("min.bf16x2 %0, %1, %2;" : "=r"(r) : "r"(a), "r"(b)); return r; }
__device__ __forceinline__ uint32_t hmaxabs(uint32_t a, uint32_t b) { uint32_t r; asm("max.xorsign.abs.bf16x2 %0, %1, %2;" : "=r"(r) : "r"(a), "r"(b)); return r; }
__device__ __forceinline__ float ex2(float x) { float r; asm("ex2.approx.ftz.f32 %0, %1;" : "=f"(r) : "f"(x)); return r; }
__device__ __forceinline__ float rcp_fast(float x) { float r; asm("rcp.approx.ftz.f32 %0, %1;" : "=f"(r) : "f"(x)); return r; }
__device__ __forceinline__ uint32_t phi2(float lo, float hi) {
  uint32_t t;
  asm("cvt.rn.relu.bf16x2.f32 %0, %1, %2;" : "=r"(t) : "f"(hi), "f"(lo));
  const uint32_t e = pk2(ex2(lo * 1.4426950408889634f), ex2(hi * 1.4426950408889634f));
  return hadd(hadd(t, hmin(e, 0x3F803F80u)), 0x35863586u);
}
__device__ __forceinline__ bool opaque_true() { uint32_t v; asm volatile("mov.u32 %0, %%nctaid.y;" : "=r"(v)); return v != 0; }
__device__ __forceinline__ int norm_exp(uint32_t (&v)[32], float f0) {
  uint32_t m[4] = {hmaxabs(__float_as_uint(f0) >> 16, v[0]), v[1], v[2], v[3]};
#pragma unroll
  for (int i = 4; i < 32; i++) m[i & 3] = hmaxabs(m[i & 3], v[i]);
  m[0] = hmaxabs(hmaxabs(m[0], m[1]), hmaxabs(m[2], m[3]));
  const int e = min(max((int)(__reduce_max_sync(~0u, max(m[0] & 0x7FFFu, (m[0] >> 16) & 0x7FFFu)) >> 7), 1), 253);
  if (e > 141) {
#pragma unroll
    for (int i = 0; i < 32; i++) v[i] = hmul(v[i], 0x07000700u);
  }
  return e;
}
__device__ __forceinline__ void norm_cvt(uint32_t (&v)[32], float f0, int e) {
  const uint32_t sc = (e > 141 ? 255 - e : 142 - e) * 0x00800080u;
#pragma unroll
  for (int i = 0; i < 32; i++) {
    const uint32_t a = hmul(v[i], sc);
    v[i] = (a & 0x0FFF0FFFu) * 7 + a;
  }
  v[0] = __byte_perm(v[0], __half_as_ushort(__float2half_rn(f0 * __uint_as_float((254 - e) << 23))), 0x3254);
}
__device__ __forceinline__ void poll_ge(const unsigned* p, unsigned target) {
#pragma unroll 1
  for (int n = 0; n < SPIN_LIMIT; n++) {
    unsigned v;
    asm volatile("ld.relaxed.gpu.global.u32 %0, [%1];" : "=r"(v) : "l"(p) : "memory");
    if (__all_sync(~0u, (int)(v - target) >= 0)) { asm volatile("fence.acquire.gpu;" ::: "memory"); return; }
  }
  __trap();
}

__device__ __forceinline__ bool elect_one() {
  uint32_t p;
  asm volatile("{\n.reg .pred p;\nelect.sync _|p, 0xffffffff;\nselp.u32 %0, 1, 0, p;\n}\n" : "=r"(p));
  return p;
}
__device__ __forceinline__ uint4 ld_na4(const void* p) {
  uint4 v;
  asm volatile("ld.global.L1::no_allocate.v4.u32 {%0,%1,%2,%3}, [%4];" : "=r"(v.x), "=r"(v.y), "=r"(v.z), "=r"(v.w) : "l"(p) : "memory");
  return v;
}
__device__ __forceinline__ void st_cg4(void* p, uint4 v) {
  asm volatile("st.global.cg.v4.u32 [%0], {%1,%2,%3,%4};" ::"l"(p), "r"(v.x), "r"(v.y), "r"(v.z), "r"(v.w) : "memory");
}
__device__ __forceinline__ uint32_t mapa(uint32_t a, uint32_t cta) { uint32_t r; asm("mapa.shared::cluster.u32 %0, %1, %2;" : "=r"(r) : "r"(a), "r"(cta)); return r; }
__device__ __forceinline__ void st_async(uint32_t a, uint32_t v, uint32_t bar) {
  asm volatile("st.async.weak.shared::cluster.mbarrier::complete_tx::bytes.b32 [%0], %1, [%2];" ::"r"(a), "r"(v), "r"(bar) : "memory");
}
__device__ __forceinline__ void st_async4(uint32_t a, uint32_t x, uint32_t y, uint32_t z, uint32_t w, uint32_t bar) {
  asm volatile("st.async.weak.shared::cluster.mbarrier::complete_tx::bytes.v4.b32 [%0], {%1,%2,%3,%4}, [%5];" ::"r"(a), "r"(x), "r"(y), "r"(z), "r"(w), "r"(bar) : "memory");
}
__device__ __forceinline__ void tma3d_st(const CUtensorMap* m, uint32_t src, int c0, int c1, int c2) {
  asm volatile("cp.async.bulk.tensor.3d.global.shared::cta.bulk_group [%0, {%2, %3, %4}], [%1];" ::"l"(m), "r"(src), "r"(c0), "r"(c1), "r"(c2) : "memory");
}
__device__ __forceinline__ uint4 ld_rlx4(const void* p) {
  uint4 v;
  asm volatile("{\n.reg .b128 t;\n.reg .b64 a, b;\nld.relaxed.gpu.global.b128 t, [%4];\nmov.b128 {a, b}, t;\nmov.b64 {%0, %1}, a;\nmov.b64 {%2, %3}, b;\n}\n"
               : "=r"(v.x), "=r"(v.y), "=r"(v.z), "=r"(v.w) : "l"(p) : "memory");
  return v;
}
__device__ __forceinline__ void ld_stale4(uint4& v, const void* p, uint32_t tag) {
  asm volatile("{\n.reg .b128 t;\n.reg .b64 a, b;\n.reg .b32 x;\n.reg .pred p;\n"
               "lop3.b32 x, %0, %5, 1, 0x28;\nsetp.ne.u32 p, x, 0;\n"
               "mov.b64 a, {%0, %1};\nmov.b64 b, {%2, %3};\nmov.b128 t, {a, b};\n"
               "@p ld.relaxed.gpu.global.b128 t, [%4];\n"
               "mov.b128 {a, b}, t;\nmov.b64 {%0, %1}, a;\nmov.b64 {%2, %3}, b;\n}\n"
               : "+r"(v.x), "+r"(v.y), "+r"(v.z), "+r"(v.w) : "l"(p), "r"(tag) : "memory");
}
__device__ __forceinline__ void st_tag4(void* p, float a, float b, float c, float d, uint32_t tag) {
  asm volatile("{\n.reg .b128 t;\n.reg .b64 a, b;\nmov.b64 a, {%1, %2};\nmov.b64 b, {%3, %4};\nmov.b128 t, {a, b};\nst.relaxed.gpu.global.b128 [%0], t;\n}\n"
               ::"l"(p), "r"((__float_as_uint(a) & ~1u) | tag), "f"(b), "f"(c), "f"(d) : "memory");
}
__device__ __forceinline__ uint32_t stale8(const uint4 (&f)[8], uint32_t tag) {
  uint32_t r[4];
#pragma unroll
  for (int i = 0; i < 4; i++) asm("lop3.b32 %0, %1, %2, %3, 0x7E;" : "=r"(r[i]) : "r"(f[2 * i].x), "r"(f[2 * i + 1].x), "r"(tag));
  asm("lop3.b32 %0, %0, %1, %2, 0xFE;" : "+r"(r[0]) : "r"(r[1]), "r"(r[2]));
  return r[0] | r[3];
}

struct ConvC { uint32_t a1[2][4], wa[2], wb[2], sg; };
__device__ __forceinline__ uint64_t dsc(uint32_t lo, uint32_t hi) { return ((uint64_t)hi << 32) | lo; }
__device__ __forceinline__ uint32_t hfma(uint32_t a, uint32_t b, uint32_t c) { uint32_t r; asm("fma.rn.f16x2 %0, %1, %2, %3;" : "=r"(r) : "r"(a), "r"(b), "r"(c)); return r; }
__device__ __forceinline__ uint32_t hfnma(uint32_t a, uint32_t b, uint32_t c) { uint32_t r; asm("{.reg .b32 n; neg.f16x2 n, %1; fma.rn.f16x2 %0, n, %2, %3;}" : "=r"(r) : "r"(a), "r"(b), "r"(c)); return r; }
__device__ __forceinline__ uint32_t hmul16(uint32_t a, uint32_t b) { uint32_t r; asm("mul.rn.f16x2 %0, %1, %2;" : "=r"(r) : "r"(a), "r"(b)); return r; }
template <int N> __device__ __forceinline__ void keepu(uint32_t (&d)[N]) {
#pragma unroll
  for (int i = 0; i < N; i++) asm volatile("" : "+r"(d[i])::"memory");
}
__device__ __forceinline__ void conv_m1(const ConvC& K, uint32_t (&u)[16], uint32_t l) {
  wg_fence();
  wgmma_hrs_n64<1>(u, K.a1[0][0], K.a1[0][1], K.a1[0][2], K.a1[0][3], dsc(l, 32), 0);
  wgmma_hrs_n64<1>(u, K.a1[1][0], K.a1[1][1], K.a1[1][2], K.a1[1][3], dsc(l + 16, 32), 1);
  wg_commit();
}
__device__ __forceinline__ void conv_s2(const ConvC& K, uint32_t (&u)[16], uint32_t (&Z)[2][8], uint32_t dfl) {
  uint32_t fr[8], fi[8];
#pragma unroll
  for (int c = 0; c < 8; c++) {
    const uint32_t r = hfma(K.wa[c & 1], u[2 * c + 1], u[2 * c]);
    fi[c] = hfma(K.wb[c & 1], r, u[2 * c + 1]);
    fr[c] = hfma(K.wa[c & 1], fi[c], r);
  }
  wg_fence();
#pragma unroll
  for (int p = 0; p < 2; p++) {
    wgmma_hrs_n32<0>(Z[p], fr[4 * p], fr[4 * p + 2], fr[4 * p + 1], fr[4 * p + 3], dsc(dfl, 32), 0);
    wgmma_hrs_n32<0>(Z[p], fi[4 * p], fi[4 * p + 2], fi[4 * p + 1], fi[4 * p + 3], dsc(dfl + 16, 32), 1);
  }
  wg_commit();
}
__device__ __forceinline__ void conv_win(const ConvC& K, const uint32_t (&X)[2][8], uint32_t (&W)[2][8]) {
#pragma unroll
  for (int b = 0; b < 4; b++)
#pragma unroll
    for (int c = 0; c < 2; c++) {
      const uint32_t xr = X[b >> 1][2 * c + (b & 1)], xi = X[b >> 1][4 + 2 * c + (b & 1)];
      const int a = b ? b - 1 : 0;
      W[b >> 1][2 * c + (b & 1)] = b ? hfnma(K.sg, X[a >> 1][4 + 2 * c + (a & 1)], xr) : hmul16(xr, 0x3C003C00u);
      W[b >> 1][4 + 2 * c + (b & 1)] = b ? hfma(K.sg, X[a >> 1][2 * c + (a & 1)], xi) : hmul16(xi, 0x3C003C00u);
    }
}
template <int p>
__device__ __forceinline__ void conv_pw(uint32_t (&X)[2][8], uint32_t (&H)[2][8], uint32_t (&V)[8], uint32_t dil) {
  uint32_t pr[2][2], pi[2][2];
#pragma unroll
  for (int jj = 0; jj < 2; jj++)
#pragma unroll
    for (int c = 0; c < 2; c++) {
      const int j = 2 * p + jj;
      uint32_t sr = 0, si = 0;
#pragma unroll
      for (int a = 0; a <= j; a++) {
        const int b = j - a;
        const uint32_t hr = H[a >> 1][2 * c + (a & 1)], hi = H[a >> 1][4 + 2 * c + (a & 1)];
        const uint32_t xr = X[b >> 1][2 * c + (b & 1)], xi = X[b >> 1][4 + 2 * c + (b & 1)];
        sr = a == 0 ? hmul16(hr, xr) : hfma(hr, xr, sr);
        si = a == 0 ? hmul16(hr, xi) : hfma(hr, xi, si);
        sr = hfnma(hi, xi, sr);
        si = hfma(hi, xr, si);
      }
      pr[jj][c] = sr; pi[jj][c] = si;
    }
  wg_fence();
  wgmma_hrs_n32<0>(V, pr[0][0], pr[1][0], pr[0][1], pr[1][1], dsc(dil, 32), 0);
  wgmma_hrs_n32<0>(V, pi[0][0], pi[1][0], pi[0][1], pi[1][1], dsc(dil + 16, 32), 1);
  wg_commit();
}
template <int p>
__device__ __forceinline__ void conv_it(const ConvC& K, uint32_t (&V)[8], uint32_t vst) {
#pragma unroll
  for (int jj = 0; jj < 2; jj++) {
    uint32_t wr[2], wi[2];
#pragma unroll
    for (int c = 0; c < 2; c++) {
      const uint32_t r = hfnma(K.wa[c], V[4 + 2 * c + jj], V[2 * c + jj]);
      wi[c] = hfnma(K.wb[c], r, V[4 + 2 * c + jj]);
      wr[c] = hfnma(K.wa[c], wi[c], r);
    }
    stsm4(vst + (2 * p + jj) * 2048, wr[0], wr[1], wi[0], wi[1]);
  }
}
__device__ __forceinline__ void conv_m4(uint32_t (&y)[8], uint32_t (&a)[4][4], uint32_t d4l) {
  wg_fence();
  wgmma_hrs_n32<0>(y, a[0][0], a[0][1], a[0][2], a[0][3], dsc(d4l, 64), 0);
#pragma unroll
  for (int s = 1; s < 4; s++) wgmma_hrs_n32<0>(y, a[s][0], a[s][1], a[s][2], a[s][3], dsc(d4l + s * 16, 64), 1);
  wg_commit();
}

struct Params {
  CUtensorMap tmX0, tmW, tmX, tmWo, tmWo1, tmK, tmV, tmQ, tmOA, tmOB;
  const __nv_bfloat16 *shift_k, *h, *D, *x, *w, *wo, *q;
  float *part, *kv;
  uint4* o;
  const uint32_t *thr, *img;
};

__global__ void __cluster_dims__(2, 1, 1) __launch_bounds__(384, 1) fused_kernel(const __grid_constant__ Params P) {
  extern __shared__ __align__(1024) uint8_t smem[];
  const uint32_t sb = __shfl_sync(~0u, smem_u32(smem), 0);
  const uint32_t bars = sb + OFF_BAR;
  const int tid = threadIdx.x, lane = tid & 31;
  const int warp = __shfl_sync(~0u, tid >> 5, 0);
  const int rank = blockIdx.x & 1, pc = blockIdx.x >> 1;
  const unsigned c7 = pc + 6, g7 = (c7 * 37) >> 8;
  const int mb = pc < 4 ? 4 + pc : pc < 36 ? (pc - 4) >> 3 : g7 - 2;
  const int hq = pc < 4 ? 0 : pc < 36 ? (pc - 4) & 7 : 1 + c7 - 7 * g7;
  const int cl = 8 * hq + mb;
  const int hp = 2 * hq + rank;
  const int rb = 2 * mb + (hq >> 2), cb = hq & 3;
#define BAR(i) (bars + 8 * (i))
#define OCNT(rb, hh) ((unsigned*)(P.o + (rb) * OBLK + 16 * 1024 + 8 * (hh)))
#define EPOCH (OCNT(rb, 2)[hp & 7])

  if (tid == 0) { STAMP(0, 0); GSTAMP(0, 30); }
  if (warp == 8) {
    if (elect_one()) {
      mbar_init(BAR(B_FULL1), 1);
      mbar_init(BAR(B_FIRST), 1);
      asm volatile("fence.mbarrier_init.release.cluster;" ::: "memory");
      mbar_expect(BAR(B_FIRST), STAGE_BYTES - 16384);
      tma2d(sb, &P.tmX0, 0, mb * 256, BAR(B_FIRST));
      tma2d(sb + 16384, &P.tmX0, 0, mb * 256 + 128, BAR(B_FIRST));
      tma3d(sb + 32768, &P.tmW, hp * 64, 0, 0, BAR(B_FIRST));
    }
    if (lane == 0) STAMP(3, 21);
  } else if (lane == 0) {
    const int wi = warp - (warp > 8);
#pragma unroll
    for (int r = 0; r < 6; r++)
      if (r < 5 || wi < B_COUNT - 56) mbar_init(BAR(1 + 11 * r + wi), ((uint32_t)(bar_counts(r) >> (4 * wi)) & 15) + 1);
    asm volatile("fence.mbarrier_init.release.cluster;" ::: "memory");
  }
  if (tid == 0) STAMP(2, 6);
  asm volatile("barrier.cluster.arrive.relaxed.aligned;\nbarrier.cluster.wait.aligned;" ::: "memory");
  if (warp == 8 && elect_one()) {
    mbar_expect(BAR(B_FULL1), 16384);
    tma2d_mc(sb + 8192 + rank * 16384, &P.tmX0, 0, mb * 256 + 64 + rank * 128, BAR(B_FULL1));
  }
  if (tid == 256) STAMP(2, 7);

  if (warp < 8) {
    asm volatile("setmaxnreg.inc.sync.aligned.u32 224;");
    const int wg = warp >> 2, w = warp & 3, g = lane >> 2, q = lane & 3, t = tid & 127;
    const bool elect = (t == 0);
    const uint32_t s16 = (sb & 0x3FFFF) >> 4;
    uint32_t pq[2][16], ux[16], uh[16], X[4][2][8], H[4][2][8];
    ConvC K;
    const uint32_t dfl = s16 + (OFF_F2F >> 4) + (8 << 16), dil = s16 + (OFF_F2I >> 4) + (8 << 16), d4l = s16 + (OFF_F4 >> 4) + (8 << 16);
    const uint32_t xl = s16 + (OFF_XT >> 4) + 4 * wg * (XT_STRIDE >> 4) + (8 << 16);
    const uint32_t hl = s16 + (OFF_H >> 4) + wg * 512 + (8 << 16);
    {
      float acc[2][96];
      if (SPLIT0) {
#pragma unroll
        for (int mt = 0; mt < 2; mt++) {
          mbar_wait(BAR(mt ? B_FULL1 : B_FIRST), 0);
          if (mt == 0 && elect) { STAMP(wg, 1); GSTAMP(wg, 26); }
          wg_fence();
#pragma unroll
          for (int ks = 0; ks < 4; ks++)
            wgmma_ss_n192<0, 1>(acc[mt], dsc(s16 + wg * 1024 + mt * 512 + (1 << 16) + ks * 2, SW128), dsc(s16 + 2048 + (512 << 16) + ks * 128, SW128), ks != 0);
        }
        wg_commit();
      }
      int st = SPLIT0 ? 1 : 0, ph = 0;
#pragma unroll 1
      for (int kb = SPLIT0 ? 1 : 0; kb < 14; kb++) {
        mbar_wait(BAR(B_FULL1 + st), ph);
        if (kb == 0 && elect) { STAMP(wg, 1); GSTAMP(wg, 26); }
        if (kb == 8 && elect) { STAMP(wg, 16); GSTAMP(wg, 25); }
        const uint32_t da = s16 + st * (STAGE_BYTES >> 4) + wg * 1024 + (1 << 16);
        const uint32_t db = s16 + st * (STAGE_BYTES >> 4) + 2048 + (512 << 16);
        wg_fence();
#pragma unroll
        for (int ks = 0; ks < 4; ks++) {
          wgmma_ss_n192<0, 1>(acc[0], dsc(da + ks * 2, SW128), dsc(db + ks * 128, SW128), (kb | ks) != 0);
          wgmma_ss_n192<0, 1>(acc[1], dsc(da + 512 + ks * 2, SW128), dsc(db + ks * 128, SW128), (kb | ks) != 0);
        }
        wg_commit();
        wg_wait<1>();
        if (kb > 0 && t < 2) mbar_arrive_cl(BAR(B_EMPTY1 + (st == 0 ? 2 : st - 1)), t);
        if (++st == 3) { st = 0; ph ^= 1; }
      }
#define TAIL_MMA(mt, stage) do { wg_fence(); _Pragma("unroll") for (int ks = 0; ks < 4; ks++) \
        wgmma_ss_n192<0, 1>(acc[mt], dsc(s16 + (stage) * (STAGE_BYTES >> 4) + wg * 1024 + (mt) * 512 + (1 << 16) + ks * 2, SW128), \
                            dsc(s16 + (stage) * (STAGE_BYTES >> 4) + 2048 + (512 << 16) + ks * 128, SW128), 1); wg_commit(); } while (0)
      mbar_wait(BAR(B_FULL1 + 2), 0);
      TAIL_MMA(0, 2);
      wg_wait<1>();
      if (elect) mbar_arrive(BAR(B_SFREE));
      mbar_wait(BAR(B_FULL1 + 0), 1);
      TAIL_MMA(0, 0);
      TAIL_MMA(1, 2);
      const uint32_t lrow = sb + wg * 16384 + (16 * w + 8 * ((lane >> 3) & 1) + (lane & 7)) * 128 + (((lane >> 4) ^ (lane & 7)) << 4);
#define E1K(mt, i) do { if (opaque_true()) { _Pragma("unroll") for (int j = (i); j < (i) + 2; j++) { \
          const float* a = &acc[mt][32 + 8 * j]; const float* b = a + 32; const uint32_t o = (lrow ^ (j * 32)) + (mt) * 8192; \
          stsm4(o + 2 * STAGE_BYTES, pk2(b[0], b[1]), pk2(b[2], b[3]), pk2(b[4], b[5]), pk2(b[6], b[7])); \
          stsm4(o, phi2(a[0], a[1]), phi2(a[2], a[3]), phi2(a[4], a[5]), phi2(a[6], a[7])); } } } while (0)
#define E1Q(mt) do { if (opaque_true()) { _Pragma("unroll") for (int i = 0; i < 16; i++) pq[mt][i] = phi2(acc[mt][2 * i], acc[mt][2 * i + 1]); } } while (0)
#define LOAD_K() do { const uint4* ct = (const uint4*)P.thr + t; \
        _Pragma("unroll") for (int s = 0; s < 2; s++) { const uint4 u = ld_na4(ct + s * 128); K.a1[s][0] = u.x; K.a1[s][1] = u.y; K.a1[s][2] = u.z; K.a1[s][3] = u.w; } \
        const uint4 u = ld_na4(ct + 2 * 128); K.wa[0] = u.x; K.wa[1] = u.y; K.wb[0] = u.z; K.wb[1] = u.w; \
        K.sg = (lane & 4) ? 0xBC00BC00u : 0x3C003C00u; } while (0)
#define PK_READY(mt) do { fence_async(); __syncwarp(); if (lane == 0) mbar_arrive(BAR(B_PKRDY + (mt))); } while (0)
      wg_wait<1>();
      keep(acc[0]);
      if (elect) STAMP(wg, 18);
      E1K(0, 0);
      TAIL_MMA(1, 0);
      E1K(0, 2);
      if (elect) STAMP(wg, 19);
      PK_READY(0);
      wg_wait<0>();
      keep(acc[1]);
      if (elect) mbar_arrive(BAR(B_G1DONE));
      asm volatile("setmaxnreg.dec.sync.aligned.u32 %0;" ::"n"(RC));
      if (elect) { STAMP(wg, 2); GSTAMP(wg, 27); }
      E1K(1, 0);
      if (elect) STAMP(wg, 20);
      E1K(1, 2);
      if (elect) STAMP(wg, 21);
      PK_READY(1);
      if (elect) STAMP(wg, 3);
      LOAD_K();
      if (elect) STAMP(wg, 4);
      E1Q(0);
      E1Q(1);
      if (elect) STAMP(wg, 17);
      mbar_wait(BAR(B_H), 0);
      conv_m1(K, ux, xl);
      conv_m1(K, uh, hl);
      wg_wait<1>(); keepu(ux);
      if (lane == 0) mbar_arrive_cl(BAR(B_XFREE + 4 * wg), rank ^ 1);
      conv_s2(K, ux, X[0], dfl);
      wg_wait<1>(); keepu(uh);
      conv_s2(K, uh, H[0], dfl);
    }
    if (elect) STAMP(wg, 5);
    float acc[64];
#define G2_MMA(da, db, first) do { wg_fence(); _Pragma("unroll") for (int ks = 0; ks < 4; ks++) \
        wgmma_ss_n128<0, 1>(acc, dsc((da) + ks * 2, SW128), dsc((db) + ks * 128, SW128), ks || !(first)); wg_commit(); } while (0)
    const uint32_t a0 = s16 + wg * 512 + (1 << 16), b0 = s16 + (512 << 16);
    uint32_t cons = mapa(BAR(B_CONS2 - 1 + G2E), t & 1);
    const bool rel = __shfl_sync(~0u, t, lane) < 2;
    {
      uint32_t vst = sb + wg * 8192 + w * 512 + lane * 16, vld = sb + wg * 8192 + w * 2048 + lane * 16;
      uint32_t ya = mapa(sb + OFF_XT + 4 * wg * XT_STRIDE + (2 * rank + (w & 1)) * 1024 + lane * 16, w >> 1);
      const uint32_t ybar = mapa(BAR(B_Y), w >> 1);
      asm volatile("" : "+r"(vst), "+r"(vld), "+r"(ya));
      uint32_t W[2][8], V0[8], V1[8], y[8], a[4][4];
      uint4 ov[4];
      uint4* const ot = P.o + (2 * mb + wg) * OBLK + hq * 1024 + (16 * w + g) * 8 + ((4 * rank + q) ^ g);
#define YOUT(i) do { if ((w >> 1) == rank) { \
          asm volatile("st.shared.v4.b32 [%0], {%1,%2,%3,%4};" ::"r"(ya + (i) * XT_STRIDE), "r"(y[0]), "r"(y[2]), "r"(y[4]), "r"(y[6]) : "memory"); \
          asm volatile("st.shared.v4.b32 [%0], {%1,%2,%3,%4};" ::"r"(ya + (i) * XT_STRIDE + 512), "r"(y[1]), "r"(y[3]), "r"(y[5]), "r"(y[7]) : "memory"); \
        } else { \
          mbar_wait(BAR(B_XFREE + 4 * wg + (i)), 0); \
          st_async4(ya + (i) * XT_STRIDE, y[0], y[2], y[4], y[6], ybar); \
          st_async4(ya + (i) * XT_STRIDE + 512, y[1], y[3], y[5], y[7], ybar); } } while (0)
      auto ocalc = [&](const int hh) {
        if (hh == 0) {
          if (elect) STAMP(wg, 8);
          mbar_wait(BAR(B_KV), 0);
          if (elect) STAMP(wg, 9);
        } else mbar_wait(BAR(B_KV1), 0);
        float oa[2][20];
        wg_fence();
#pragma unroll
        for (int m = 0; m < 4; m++) {
          const uint32_t* p = &pq[m & 1][8 * hh + 4 * (m >> 1)];
          wgmma_rs_n40<1>(oa[m & 1], p[0], p[1], p[2], p[3], dsc(s16 + (OFF_KVB >> 4) + hh * 160 + (m >> 1) * 16 + (8 << 16), 32), m >> 1);
        }
        wg_commit();
        wg_wait<0>();
#pragma unroll
        for (int mt = 0; mt < 2; mt++) {
          float (&o)[20] = oa[mt];
          keep(o);
          const uint32_t den = hadd(pk2(o[16], o[18]), 0x35863586u);
#pragma unroll
          for (int r = 0; r < 2; r++) {
            const float ri = rcp_fast(__uint_as_float(r ? (den & 0xFFFF0000u) : (den << 16)));
            uint4 u;
            u.x = pk2(o[2 * r] * ri, o[2 * r + 1] * ri);
            u.y = pk2(o[4 + 2 * r] * ri, o[5 + 2 * r] * ri);
            u.z = pk2(o[8 + 2 * r] * ri, o[9 + 2 * r] * ri);
            u.w = pk2(o[12 + 2 * r] * ri, o[13 + 2 * r] * ri);
            if (hh == 0) st_cg4(ot + (64 * mt + 8 * r) * 8, u); else ov[2 * mt + r] = u;
          }
        }
        if (hh == 0) {
          __syncwarp();
          if (lane == 0) mbar_arrive(BAR(B_ODONE));
          if (elect) STAMP(wg, 10);
        }
      };
      auto trickle = [&](const int qs) {
        const int m = qs - 2 * (OCH + O1D) - (TRICK - 1);
        if (m >= 0 && m < 4) {
          st_cg4(ot + 8 * 1024 + (64 * (m >> 1) + 8 * (m & 1)) * 8, ov[m]);
          if (m == 3) { __syncwarp(); if (lane == 0) mbar_arrive(BAR(B_ODONE1)); }
        }
      };
#pragma unroll
      for (int i = 0; i < 4; i++) {
        const bool nx = i < 3;
        const int n = nx ? i + 1 : i;
        const uint32_t vo = (i & 1) ? OFF_H + (i >> 1) * 16384 : OFF_VP;
        if (2 * i == OCH) ocalc(0);
        if (2 * i == OCH + O1D) ocalc(1);
        if (nx) {
          conv_m1(K, ux, xl + n * (XT_STRIDE >> 4));
          conv_m1(K, uh, hl + (n >> 1) * 1024 + (n & 1) * 256);
        }
        if (2 * i != OCH && 2 * i != OCH + O1D) { if (nx) { if (i > 0) wg_wait<3>(); else wg_wait<2>(); } else wg_wait<1>(); }
        keepu(X[i][0]); keepu(X[i][1]); keepu(H[i][0]); keepu(H[i][1]);
        conv_win(K, X[i], W);
        trickle(4 * i);
        conv_pw<0>(W, H[i], V0, dil);
        conv_pw<1>(W, H[i], V1, dil);
        trickle(4 * i + 1);
        wg_wait<2>();
        if (i > 0) { keepu(y); YOUT(i - 1); }
        if (2 * i + 1 == OCH) ocalc(0);
        if (2 * i + 1 == OCH + O1D) ocalc(1);
        if (nx) {
          keepu(ux); keepu(uh);
          if (lane == 0) mbar_arrive_cl(BAR(B_XFREE + 4 * wg + n), rank ^ 1);
          conv_s2(K, ux, X[n], dfl);
          wg_wait<1>();
        } else wg_wait<0>();
        keepu(V0); keepu(V1);
        if (G2E && G2P == 0 && i == 3) { mbar_wait(BAR(B_FULL2), 0); G2_MMA(a0 + (SLOT_A & 15) * 1024, b0 + (SLOT_B & 15) * 1024, true); }
        trickle(4 * i + 2);
        if (i == 0) mbar_wait(BAR(B_H2), 0);
        conv_it<0>(K, V0, vst + vo);
        conv_it<1>(K, V1, vst + vo);
        if (G2E && G2P == 1 && i == 3) { mbar_wait(BAR(B_FULL2), 0); G2_MMA(a0 + (SLOT_A & 15) * 1024, b0 + (SLOT_B & 15) * 1024, true); }
        bar_sync(1 + wg);
#pragma unroll
        for (int s = 0; s < 4; s++) ldsm4t(a[s], vld + vo + s * 512);
        if (nx) conv_s2(K, uh, H[n], dfl);
        conv_m4(y, a, d4l);
        trickle(4 * i + 3);
        if (i > 0 && lane < 2) mbar_arrive_cl(BAR(B_AFREE + i - 1), lane);
        if (elect && i < 3) STAMP(wg, i < 2 ? 6 + i : 9 + i);
      }
      if (G2E && G2P == 2) { mbar_wait(BAR(B_FULL2), 0); G2_MMA(a0 + (SLOT_A & 15) * 1024, b0 + (SLOT_B & 15) * 1024, true); wg_wait<1>(); }
      else wg_wait<0>();
      keepu(y);
      if (G2E && G2P < 2 && rel) asm volatile("mbarrier.arrive.shared::cluster.b64 _, [%0];" ::"r"(cons) : "memory");
      YOUT(3);
      __syncwarp();
      if (lane == 0) mbar_arrive(BAR(B_Y));
      if (elect) STAMP(wg, 12);
    }
    {
      uint64_t ta = SLOT_A >> (4 * G2E), tb = SLOT_B >> (4 * G2E);
      uint32_t da = a0 + ((uint32_t)ta & 15) * 1024, db = b0 + ((uint32_t)tb & 15) * 1024, fb = BAR(B_FULL2 + G2E);
#pragma unroll 1
      for (int kb = G2E; kb < HOLD2; kb++) {
        mbar_wait(fb, 0);
        if (kb == G2E && elect) { STAMP(wg, 13); GSTAMP(wg, 28); }
        G2_MMA(da, db, kb == 0);
        ta >>= 4; tb >>= 4;
        da = a0 + ((uint32_t)ta & 15) * 1024; db = b0 + ((uint32_t)tb & 15) * 1024; fb += 8;
        asm volatile("" : "+r"(da), "+r"(db));
        wg_wait<1>();
        if ((kb > G2E || (G2E && G2P == 2)) && kb < 12 && rel) asm volatile("mbarrier.arrive.shared::cluster.b64 _, [%0];" ::"r"(cons) : "memory");
        cons += 8;
      }
#pragma unroll
      for (int kb = HOLD2; kb < 16; kb++) {
        if (wg == 1) mbar_wait(BAR(B_FULL2 + kb), 0);
        else if (kb == HOLD2) asm volatile("bar.sync 3, 256;" ::: "memory");
        G2_MMA(a0 + ((SLOT_A >> (4 * kb)) & 15) * 1024, b0 + ((SLOT_B >> (4 * kb)) & 15) * 1024, false);
      }
      if (wg == 1) asm volatile("bar.arrive 3, 256;" ::: "memory");
      const uint32_t stg = sb + wg * 8192 + w * 2048, so0 = ((SLOT_A >> 56) & 15) * 16384, so1 = ((SLOT_A >> 60) & 15) * 16384;
      const uint32_t lrow = stg + (8 * ((lane >> 3) & 1) + (lane & 7)) * 128 + (((lane >> 4) ^ (lane & 7)) << 4);
      const int col = 1024 + 256 * cb + 128 * rank, row = 128 * rb + 64 * wg + 16 * w;
      wg_wait<0>();
      keep(acc);
      if (elect) { STAMP(wg, 14); GSTAMP(wg, 29); }
#pragma unroll
      for (int cp = 0; cp < 8; cp++) {
        const float* a = &acc[8 * cp];
        stsm4((lrow ^ ((cp & 3) * 32)) + (cp >> 2 ? so1 : so0), pk2(a[0], a[1]), pk2(a[2], a[3]), pk2(a[4], a[5]), pk2(a[6], a[7]));
        if ((cp & 3) == 3) {
          fence_async();
          __syncwarp();
          if (elect_one()) tma2d_st(&P.tmOB, stg + (cp >> 2 ? so1 : so0), col + (cp >> 2) * 64, row);
        }
      }
      asm volatile("cp.async.bulk.commit_group;\ncp.async.bulk.wait_group.read 0;" ::: "memory");
      if (elect) {
        STAMP(wg, 15); GSTAMP(wg, 31); PDUMP(wg); if (wg == 0) PDUMP(2);
      }
    }
  } else {
    asm volatile("setmaxnreg.dec.sync.aligned.u32 56;");
    const int hw = warp - 9, g = lane >> 2, q = lane & 3;
#define sbar (bars + 8 * (B_STG - 18) + 16 * warp)
    if (warp == 8) {
      if (D1) __nanosleep(D1);
      int st = 1, pp = 1;
      const uint8_t* pfx = (const uint8_t*)P.x + (mb * 256 + hp * 16 + (lane & 15)) * 2048;
      const uint8_t* pfw = (const uint8_t*)P.w + (mb * 8 + (lane & 7)) * 6144 + (lane >> 3) * 2048 + hp * 128;
#pragma unroll 1
      for (int kb = 1; kb < 16; kb++) {
        if (kb >= 3) mbar_wait(BAR(B_EMPTY1 + st), pp);
        const uint32_t sa = sb + st * STAGE_BYTES;
        if (elect_one()) {
          mbar_expect(BAR(B_FULL1 + st), STAGE_BYTES);
          tma2d_mc(sa + rank * 16384, &P.tmX, kb * 64, mb * 256 + rank * 128, BAR(B_FULL1 + st));
          tma3d(sa + 32768, &P.tmW, hp * 64, kb * 64, 0, BAR(B_FULL1 + st));
        }
        if (kb == 1 && lane == 0) STAMP(2, 24);
        if (PFD && kb >= 2) {
#pragma unroll 1
          for (int j = kb == 2 ? 3 : kb + PFD; j <= kb + PFD && j < 16; j++) {
            if (lane < 16) asm volatile("prefetch.global.L2 [%0];" ::"l"(pfx + j * 128));
            if (lane < 24) asm volatile("prefetch.global.L2 [%0];" ::"l"(pfw + j * (64 * 6144)));
          }
          if (kb >= QPF && kb < QPF + 8) asm volatile("prefetch.global.L2 [%0];" ::"l"((const uint8_t*)P.q + (blockIdx.x * 256 + (kb - QPF) * 32 + lane) * 128));
          if (kb >= 4)
            asm volatile("prefetch.global.L2 [%0];" ::"l"(kb < 12 ? (const uint8_t*)P.h + ((2 * cl + rank) * 256 + (kb - 4) * 32 + lane) * 128
                                                                  : (const uint8_t*)P.wo + (blockIdx.x * 128 + (kb - 12) * 32 + lane) * 128));
        }
        if (++st == 3) { st = 0; pp ^= 1; }
      }
      if (lane == 0) STAMP(2, 1);
    } else {
      {
        const uint32_t clk0 = __shfl_sync(~0u, (uint32_t)clock(), 0), stg = sb + OFF_STG + hw * STG_STRIDE;
        const unsigned epoch = __shfl_sync(~0u, EPOCH, 0);
        const uint32_t tag = ~epoch & 1;
        uint32_t tap[2][4];
#pragma unroll
        for (int cg = 0; cg < 2; cg++) {
          const uint2 u = __ldg((const uint2*)(P.shift_k + (16 * cl + 8 * cg + g) * 4));
          tap[cg][0] = __byte_perm(u.x, 0, 0x1010); tap[cg][1] = __byte_perm(u.x, 0, 0x3232);
          tap[cg][2] = __byte_perm(u.y, 0, 0x1010); tap[cg][3] = __byte_perm(u.y, 0, 0x3232);
        }
        if (hw == 0 && lane < 8) *(float*)(smem + OFF_D + 4 * lane) = __bfloat162float(P.D[16 * cl + 8 * rank + lane]);
        if (hw == 1 && lane < 24) asm volatile("prefetch.global.L2 [%0];" ::"l"(P.thr + (lane + 24 * rank) * 32));
        if (hw == 0 && elect_one()) {
          *(volatile unsigned*)(smem + OFF_EPOCH) = epoch;
          mbar_expect(BAR(B_XRAW), 16384);
          mbar_expect(BAR(B_Y), 16384 + 64);
        }
#pragma unroll 1
        for (int i = hw * 32 + lane; i < 528; i += 96) st_tag4(P.part + (hp * 8 + mb) * 2176 + 4 * i, 0.f, 0.f, 0.f, 0.f, tag ^ 1);
        if (hw < 2 || lane < 2) st_tag4(P.kv + hp * 2176 + (4 * (hw < 2 ? 64 * mb + 32 * hw + lane : 512 + 8 * (mb & 1) + (mb & 6) + lane)), 0.f, 0.f, 0.f, 0.f, tag ^ 1);
        if (lane == 0) STAMP(3, hw);
        const uint32_t xo = sb + OFF_XT + g * XT_STRIDE + rank * 2048 + q * 4;
        const int krow = 8 + (lane & 7) - (lane >> 3);
        const uint32_t ka = stg + krow * 32 + ((krow & 4) << 2), va = stg + 2304 + lane * 32 + ((lane & 4) << 2);
        int ph = 0, b = 0;
#pragma unroll 1
        for (int ci = hw - 3; ci < 16; ci += 3) {
          const uint32_t bo = b ? OFF_F2F - OFF_STG : 0, bn = b ? 0 : OFF_F2F - OFF_STG;
          if (ci + 3 < 16) {
            while (__any_sync(~0u, (uint32_t)clock() - clk0 < HSTART + (ci + 3) * PACE)) __nanosleep(64);
            if (elect_one()) {
              mbar_expect(sbar + 8 * (b ^ 1), 2304 + 2048);
              tma2d(stg + bn, &P.tmK, 16 * cl, 1024 * rank + 64 * (ci + 3) - 8, sbar + 8 * (b ^ 1));
              tma2d(stg + bn + 2304, &P.tmV, 16 * cl, 1024 * rank + 64 * (ci + 3), sbar + 8 * (b ^ 1));
            }
          }
          if (ci >= 0) {
            mbar_wait(sbar + 8 * b, (ph >> b) & 1);
            ph ^= 1 << b;
#pragma unroll 1
            for (int grp = 0; grp < 2; grp++) {
#pragma unroll
              for (int cg = 0; cg < 2; cg++) {
                const uint32_t dst = mapa(xo + (ci >> 3) * 1024 + ((ci & 7) * 4 + 2 * grp) * 16, cg), xbar = mapa(BAR(B_XRAW), cg);
                uint32_t vv[4], kk[4][4];
                ldsm4t(vv, (va ^ (cg * 16)) + bo + grp * 1024);
#pragma unroll
                for (int rg = 0; rg < 4; rg++) ldsm4t(kk[rg], (ka ^ (cg * 16)) + bo + grp * 1024 + rg * 256);
#pragma unroll
                for (int rg = 0; rg < 4; rg++)
                  vv[rg] = hmul(hadd(hadd(hadd(hmul(kk[rg][3], tap[cg][3]), hmul(kk[rg][2], tap[cg][2])), hmul(kk[rg][1], tap[cg][1])), hmul(kk[rg][0], tap[cg][0])), vv[rg]);
                if (cg == rank) {
#pragma unroll
                  for (int rg = 0; rg < 4; rg++) asm volatile("st.shared.b32 [%0], %1;" ::"r"(dst + (rg & 1) * 512 + (rg >> 1) * 16), "r"(vv[rg]) : "memory");
                } else {
#pragma unroll
                  for (int rg = 0; rg < 4; rg++) st_async(dst + (rg & 1) * 512 + (rg >> 1) * 16, vv[rg], xbar);
                }
              }
            }
          }
          b ^= 1;
        }
      }
      if (lane == 0 && hw == 0) STAMP(3, 3);
      asm volatile("bar.sync 4, 96;" ::: "memory");
      if (hw == 0 && elect_one()) { mbar_expect(BAR(B_XT), 10240); bulk_ld(sb + OFF_F2F, P.img, 10240, BAR(B_XT)); }
      mbar_wait(BAR(B_XRAW), 0);
    }
    int e1 = 0;
#pragma unroll 1
    for (int n = hw < 0 ? 3 : 0; n < 4; n++) {
      const bool isH = n >= 3;
      const int c = isH ? (warp & 1) + 2 * (warp & 2) : hw + 3 * n;
      if (c < 8) {
        int ln;
        asm volatile("mov.u32 %0, %%laneid;" : "=r"(ln));
        uint8_t* dst = smem + (isH ? OFF_H + (c & 2) * 8192 + (c >> 2) * 8192 + (c & 1) * 4096 : OFF_XT + c * XT_STRIDE) + ((ln >> 4) * 512 + (ln & 15) * 16);
        const uint8_t* src0 = isH ? (const uint8_t*)P.h + (16 * cl + 8 * rank + c) * 4096 + ((ln & 15) * 32 + (ln & 16)) : dst;
        const uint8_t* src1 = src0 + (isH ? 512 : 256);
        uint32_t v[32];
#pragma unroll
        for (int i = 0; i < 8; i++) {
          const uint4 u = *(const uint4*)(((i & 1) ? src1 : src0) + (i >> 1) * 1024);
          v[4 * i] = u.x; v[4 * i + 1] = u.y; v[4 * i + 2] = u.z; v[4 * i + 3] = u.w;
        }
        if (isH) mbar_wait(BAR(B_XT), 0);
        const float f0 = __uint_as_float(v[0] << 16) + ((isH && ln == 0) ? *(const float*)(smem + OFF_D + 4 * c) : 0.f);
        const int e = norm_exp(v, f0);
        norm_cvt(v, f0, e);
        if (isH) mbar_wait(BAR(B_SFREE), 0);
        else if (ln == 0) smem[OFF_EX + c] = e;
        e1 = e;
#pragma unroll
        for (int i = 0; i < 8; i++)
          *(uint4*)(dst + (i >> 1) * 1024 + (i & 1) * 256) = make_uint4(v[4 * i], v[4 * i + 1], v[4 * i + 2], v[4 * i + 3]);
        if (n < 2 && elect_one()) {
          if (n == 0) mbar_expect(sbar, 4096);
          tma3d(sb + OFF_STG + 2048 * c, &P.tmQ, 16 * cl, 64 * rank, 2 * c, sbar);
        }
      }
      if (n >= 2) {
        fence_async();
        __syncwarp();
        if (lane == 0) { mbar_arrive(BAR(isH ? B_H : B_XT)); STAMP(3, (isH ? 17 : 13) + hw); }
      }
    }
#define SLOT(tab, kb) (sb + ((uint32_t)((tab) >> (4 * (kb))) & 15) * 16384)
#define KT(kb) (!OLOC ? (kb) : (kb) == 0 ? hq : (kb) == hq ? 0 : (kb))
#define LOAD_B(kb) tma4d(SLOT(SLOT_B, kb), &P.tmWo, 0, ((kb) >> 3) * 32, 2 * (KT(kb) & 7), 4 * cb + 2 * rank, BAR(B_FULL2 + (kb)))
#define LOAD_A(kb) bulk_ld_mc(SLOT(SLOT_A, kb) + rank * 8192, P.o + rb * OBLK + KT(kb) * 1024 + rank * 512, 8192, BAR(B_FULL2 + (kb)))
    asm volatile("setmaxnreg.inc.sync.aligned.u32 %0;" ::"n"(504 - 2 * RC));
    {
    int tid;
    asm volatile("mov.u32 %0, %%tid.x;" : "=r"(tid));
    const int lane = tid & 31, g = lane >> 2, q = lane & 3;
    const unsigned epoch = *(volatile unsigned*)(smem + OFF_EPOCH);
    const uint32_t tag = ~epoch & 1;
    const int pi = hw < 2 ? 64 * mb - 288 + tid : 512 + 8 * (mb & 1) + (mb & 6) + (lane & 1);
    const float* psrc = P.part + hp * 8 * 2176 + 4 * pi;
    uint4 f[8];
    {
      const uint32_t s16 = (sb & 0x3FFFF) >> 4;
      const int t = tid & 127, c = 2 + (warp & 1) + 2 * (warp & 2);
      const uint4* hp4 = (const uint4*)(P.h + (16 * cl + 8 * rank + c) * 2048) + ((lane & 15) * 2 + (lane >> 4));
      uint32_t v[32];
#pragma unroll
      for (int i = 0; i < 8; i++) { const uint4 u = ld_na4(hp4 + i * 32); v[4 * i] = u.x; v[4 * i + 1] = u.y; v[4 * i + 2] = u.z; v[4 * i + 3] = u.w; }
      float kva[36];
#pragma unroll
      for (int mt = 0; mt < 2; mt++) {
        mbar_wait(BAR(B_PKRDY + mt), 0);
        wg_fence();
#pragma unroll
        for (int ks = 0; ks < 8; ks++) {
          const uint32_t o = (ks >> 2) * 1024 + mt * 512 + (ks & 3) * 128, vb = (2 * STAGE_BYTES >> 4) + o;
          wgmma_ss_n72<1, 1>(kva, dsc(s16 + o + (1 << 16), SW128), dsc(s16 + vb + (((OFF_ONES >> 4) - vb) << 16), SW128), (mt | ks) != 0);
        }
        wg_commit();
        if (mt == 0 && hw < 0) {
          mbar_wait(BAR(B_G1DONE), 0);
          if (elect_one()) {
#pragma unroll
            for (int kb = 0; kb < BEARLY; kb++) { mbar_expect(BAR(B_FULL2 + kb), 16384); LOAD_B(kb); }
          }
        }
      }
      float* pdst = P.part + (hp * 8 + mb) * 2176 + t * 4;
      float* zdst = P.part + (hp * 8 + mb) * 2176 + 2048 + (t >> 1);
      asm volatile("" : "+l"(pdst), "+l"(zdst));
      wg_wait<0>();
      keep(kva);
      if (hw < 1) {
#pragma unroll
        for (int c = 0; c < 4; c++) st_tag4(pdst + c * 512, kva[4 * c], kva[4 * c + 1], kva[4 * c + 2], kva[4 * c + 3], tag);
      } else {
#pragma unroll
        for (int c = 4; c < 8; c++) st_tag4(pdst + (c - 4) * 512, kva[4 * c], kva[4 * c + 1], kva[4 * c + 2], kva[4 * c + 3], tag);
      }
      const float z2 = __shfl_down_sync(~0u, kva[32], 4), z3 = __shfl_down_sync(~0u, kva[34], 4);
      if (!(lane & 7)) st_tag4(zdst, kva[32], kva[34], z2, z3, tag);
      if (lane == 0) mbar_arrive(BAR(B_PKFREE));
      const uint32_t cst = clock();
      if (hw == 0 && lane == 0) STAMP(3, 24);
      const float f0 = __uint_as_float(v[0] << 16) + (lane == 0 ? *(const float*)(smem + OFF_D + 4 * c) : 0.f);
      const int e = norm_exp(v, f0);
      norm_cvt(v, f0, e);
      if (hw >= 0) {
        while (__any_sync(~0u, (uint32_t)clock() - cst < PD1)) __nanosleep(20);
        if (hw == 0 && lane == 0) STAMP(3, 20);
#pragma unroll
        for (int p = 0; p < 8; p++) f[p] = ld_rlx4(psrc + p * 2176);
      }
      uint8_t* dst = smem + OFF_H + 16384 + (warp & 3) * 4096 + (lane >> 4) * 512 + (lane & 15) * 16;
#pragma unroll
      for (int i = 0; i < 8; i++)
        *(uint4*)(dst + (i >> 1) * 1024 + (i & 1) * 256) = make_uint4(v[4 * i], v[4 * i + 1], v[4 * i + 2], v[4 * i + 3]);
      if (lane < 4) {
        const int cc = c - (lane & 2);
        st_async(mapa(sb + OFF_SCALE + (8 * rank + cc) * 4, lane & 1), min(max(((lane & 2) ? e1 : e) + smem[OFF_EX + cc] - 124, 1), 254) << 23, mapa(BAR(B_Y), lane & 1));
      }
    }
#define H2_READY() do { fence_async(); __syncwarp(); if (lane == 0) mbar_arrive(BAR(B_H2)); } while (0)
    if (warp == 8) {
      H2_READY();
      mbar_wait(BAR(B_PKFREE), 0);
      {
        const uint32_t c0 = clock();
#pragma unroll 1
        for (int i = 0; i < 2 * NPRE - 2 * BEARLY; i++) {
          const int kb = (i >> 1) + BEARLY;
          while (__any_sync(~0u, (uint32_t)clock() - c0 < i * BPACE)) __nanosleep(32);
          if (elect_one()) {
            if (!(i & 1)) mbar_expect(BAR(B_FULL2 + kb), 16384);
            tma4d(SLOT(SLOT_B, kb) + (i & 1) * 8192, &P.tmWo1, 0, 0, 2 * KT(kb), 4 * cb + 2 * rank + (i & 1), BAR(B_FULL2 + kb));
            if (i == 0) mbar_expect(BAR(B_Q), 8192);
            if (i < 4) tma3d(sb + OFF_SPARE + 2048 * i, &P.tmQ, 16 * cl, 64 * rank + 32 * (i >> 1), 2 * ((i + 6) & 7), BAR(B_Q));
          }
        }
      }
      if (lane == 0) STAMP(2, 2);
      if (OLOC) {
        if (elect_one()) mbar_expect(BAR(B_FULL2), 16384);
        mbar_wait(BAR(B_OLOC), 0);
        asm volatile("fence.acquire.cluster;\nfence.proxy.async.global;" ::: "memory");
        if (elect_one()) LOAD_A(0);
      }
      mbar_wait(BAR(B_AFREE), 0);
      if (elect_one()) mbar_expect(BAR(B_FULL2 + OLOC), 16384);
      {
        const uint32_t dst = SLOT(SLOT_A, OLOC) + rank * 8192;
        const uint4* src = P.o + rb * OBLK + KT(OLOC) * 1024 + rank * 512;
        poll_ge(OCNT(rb, 0), 16 * (epoch + 1));
        asm volatile("fence.proxy.async.global;" ::: "memory");
        if (lane == 0) STAMP(2, 3);
        if (elect_one()) bulk_ld_mc(dst, src, 8192, BAR(B_FULL2 + OLOC));
        if (lane == 0) STAMP(3, 23);
      }
#pragma unroll 1
      for (int kb = 1 + OLOC; kb < NPRE; kb++) {
        mbar_wait(BAR(kb < 4 ? B_AFREE + kb - 1 : B_CONS2), 0);
        if (elect_one()) { mbar_expect(BAR(B_FULL2 + kb), 16384); LOAD_A(kb); }
      }
#pragma unroll 1
      for (int kb = NPRE; kb < 16; kb++) {
        mbar_wait(BAR(B_CONS2 + kb - 5), 0);
        if (kb == 8) mbar_wait(BAR(B_O1RDY), 0);
        if (elect_one()) { mbar_expect(BAR(B_FULL2 + kb), 32768); LOAD_A(kb); LOAD_B(kb); }
      }
      if (lane == 0) { EPOCH = epoch + 1; STAMP(2, 5); }
    } else {
      {
#pragma unroll 1
        for (int n = 0; __any_sync(~0u, stale8(f, tag) & 1); n++) {
#pragma unroll
          for (int p = 0; p < 8; p++) ld_stale4(f[p], psrc + p * 2176, tag);
          if (n > SPIN_LIMIT) __trap();
        }
        float s0 = 0.f, s1 = 0.f, s2 = 0.f, s3 = 0.f;
#pragma unroll
        for (int p = 0; p < 8; p++) { s0 += __uint_as_float(f[p].x); s1 += __uint_as_float(f[p].y); s2 += __uint_as_float(f[p].z); s3 += __uint_as_float(f[p].w); }
        if (hw < 2 || lane < 2) st_tag4(P.kv + hp * 2176 + (4 * pi), s0, s1, s2, s3, tag);
      }
      const uint32_t cs2 = clock();
      if (lane == 0 && hw == 0) STAMP(3, 8);
      H2_READY();
      if (hw == 2) {
        unsigned* cnt = OCNT(2 * mb + lane, 0);
#pragma unroll 1
        for (int hh = 0; hh < 2; hh++) {
          mbar_wait(BAR(hh ? B_ODONE1 : B_ODONE), 0);
          if (lane < 2) asm volatile("red.release.gpu.global.add.u32 [%0], 1;" ::"l"(cnt) : "memory");
          if (OLOC && hh == 0 && lane < 2) mbar_arrive_cl(BAR(B_OLOC), lane);
          cnt += 32;
          if (lane == 0) STAMP(3, hh ? 6 : 7);
        }
        poll_ge(OCNT(rb, 1), 16 * (epoch + 1));
        asm volatile("fence.proxy.async.global;" ::: "memory");
        if (lane == 0) { mbar_arrive(BAR(B_O1RDY)); STAMP(2, 4); }
        __syncwarp();
      } else {
        const int t = tid - 288;
        const float* src = P.kv + hp * 2176 + 4 * (t + 32 * hw);
        const float* zsrc = P.kv + hp * 2176 + (2048 + (t & 48) + 2 * (lane & 6));
        mbar_wait(BAR(B_PKFREE), 0);
        while (__any_sync(~0u, (uint32_t)clock() - cs2 < PD2)) __nanosleep(20);
        uint4 zp = ld_rlx4(zsrc);
#pragma unroll
        for (int p = 0; p < 8; p++) f[p] = ld_rlx4(src + 4 * ((p & 3) * 128 + (p >> 2) * 32));
        if (!opaque_true()) __trap();
#pragma unroll 1
        for (int n = 0; __any_sync(~0u, (stale8(f, tag) | (zp.x ^ tag)) & 1); n++) {
          ld_stale4(zp, zsrc, tag);
#pragma unroll
          for (int p = 0; p < 8; p++) ld_stale4(f[p], src + 4 * ((p & 3) * 128 + (p >> 2) * 32), tag);
          if (n > SPIN_LIMIT) __trap();
        }
#define PK2U(a, b) pk2(__uint_as_float(a), __uint_as_float(b))
        const uint32_t zf = (lane & 1) ? ((lane & 8) ? zp.w : zp.z) : ((lane & 8) ? zp.y : zp.x);
        const uint32_t zz = PK2U(zf, zf);
        *(uint4*)(smem + OFF_KVB + hw * 2560 + 2048 + lane * 16) = make_uint4(zz, zz, zz, zz);
#pragma unroll
        for (int hh = 0; hh < 2; hh++) {
          const uint4* ff = &f[4 * hh];
          uint8_t* dst = smem + OFF_KVB + hw * 2560 + q * 512 + (16 * hh + g) * 16;
          *(uint4*)dst = make_uint4(PK2U(ff[0].x, ff[0].y), PK2U(ff[1].x, ff[1].y), PK2U(ff[2].x, ff[2].y), PK2U(ff[3].x, ff[3].y));
          *(uint4*)(dst + 128) = make_uint4(PK2U(ff[0].z, ff[0].w), PK2U(ff[1].z, ff[1].w), PK2U(ff[2].z, ff[2].w), PK2U(ff[3].z, ff[3].w));
        }
        fence_async();
        __syncwarp();
        if (lane == 0) { mbar_arrive(BAR(hw ? B_KV1 : B_KV)); if (hw == 0) STAMP(3, 9); }
      }
#define QBUF(ci) (sb + 2048 * (ci) + ((ci) < 6 ? OFF_STG : (ci) < 10 ? OFF_SPARE - 6 * 2048 : OFF_F2F - 10 * 2048))
      mbar_wait(BAR(B_Y), 0);
      if (elect_one()) {
        mbar_expect(sbar + 8, 4096);
#pragma unroll 1
        for (int ci = hw ? hw + 9 : 12; ci < 16; ci += 3) tma3d(QBUF(ci), &P.tmQ, 16 * cl, 64 * rank + 32, 2 * (ci & 7), sbar + 8);
      }
      mbar_wait(BAR(B_Q), 0);
      mbar_wait(sbar, hw == 0);
      {
        const float2 sc0 = *(const float2*)(smem + OFF_SCALE + 8 * q), sc1 = *(const float2*)(smem + OFF_SCALE + 32 + 8 * q);
        const uint32_t yl = sb + OFF_XT + (lane & 7) * XT_STRIDE + (lane >> 3) * 16;
#pragma unroll 1
        for (int ci = hw; ci < 16; ci += 3) {
          const uint32_t qb = QBUF(ci);
          if (ci >= 10) mbar_wait(sbar + 8, 1);
#pragma unroll 1
          for (int nl = 0; nl < 2; nl++) {
            uint32_t yy[2][4], qq[2][4];
            const uint32_t qa = qb + lane * 32 + ((lane & 4) << 2) + nl * 1024;
#pragma unroll
            for (int cg = 0; cg < 2; cg++) { ldsm4t(yy[cg], yl + cg * 2048 + (2 * ci + nl) * 64); ldsm4(qq[cg], qa ^ (cg * 16)); }
#pragma unroll
            for (int cg = 0; cg < 2; cg++) {
              const float2 sc = cg ? sc1 : sc0;
#pragma unroll
              for (int m = 0; m < 4; m++) {
                const float2 f = __half22float2(*(const __half2*)&yy[cg][m]);
                qq[cg][m] = hmul(qq[cg][m], pk2(f.x * sc.x, f.y * sc.y));
              }
              stsm4(qa ^ (cg * 16), qq[cg][0], qq[cg][1], qq[cg][2], qq[cg][3]);
            }
          }
          fence_async();
          __syncwarp();
          if (elect_one()) tma3d_st(&P.tmOA, qb, 16 * cl, 64 * rank + 32 * (ci >> 3), 2 * (ci & 7));
        }
        asm volatile("cp.async.bulk.commit_group;\ncp.async.bulk.wait_group.read 0;" ::: "memory");
      }
      if (lane == 0) STAMP(3, 10 + hw);
    }
    }
  }
}

typedef CUresult (*EncodeFn)(CUtensorMap*, CUtensorMapDataType, cuuint32_t, void*, const cuuint64_t*, const cuuint64_t*,
                             const cuuint32_t*, const cuuint32_t*, CUtensorMapInterleave, CUtensorMapSwizzle,
                             CUtensorMapL2promotion, CUtensorMapFloatOOBfill);

static void enc(EncodeFn fn, CUtensorMap* m, const void* p, int rank, const cuuint64_t* dims, const cuuint64_t* strides,
                const cuuint32_t* box, CUtensorMapSwizzle swz, CUtensorMapL2promotion promo) {
  cuuint32_t es[4] = {1, 1, 1, 1};
  fn(m, CU_TENSOR_MAP_DATA_TYPE_BFLOAT16, rank, (void*)p, dims, strides, box, es, CU_TENSOR_MAP_INTERLEAVE_NONE, swz, promo,
     CU_TENSOR_MAP_FLOAT_OOB_FILL_NONE);
}

extern "C" void kernel_launch(void* const* d_in, const int* in_sizes, int n_in, void* d_out, int out_size) {
  void* fp = nullptr;
  cudaDriverEntryPointQueryResult qr;
  cudaGetDriverEntryPoint("cuTensorMapEncodeTiled", &fp, cudaEnableDefault, &qr);
  EncodeFn fn = (EncodeFn)fp;
  Params P;
  P.shift_k = (const __nv_bfloat16*)d_in[3]; P.h = (const __nv_bfloat16*)d_in[4]; P.D = (const __nv_bfloat16*)d_in[5];
  P.q = (const __nv_bfloat16*)d_in[0];
  cudaGetSymbolAddress((void**)&P.part, g_part); cudaGetSymbolAddress((void**)&P.kv, g_kv); cudaGetSymbolAddress((void**)&P.o, g_o);
  cudaGetSymbolAddress((void**)&P.thr, c_thr); cudaGetSymbolAddress((void**)&P.img, c_img);
  P.x = (const __nv_bfloat16*)d_in[6]; P.w = (const __nv_bfloat16*)d_in[7]; P.wo = (const __nv_bfloat16*)d_in[8];
  const CUtensorMapSwizzle S128 = CU_TENSOR_MAP_SWIZZLE_128B, S32 = CU_TENSOR_MAP_SWIZZLE_32B;
  const CUtensorMapL2promotion P0 = CU_TENSOR_MAP_L2_PROMOTION_NONE, P128 = CU_TENSOR_MAP_L2_PROMOTION_L2_128B;
  { cuuint64_t d[2] = {1024, 2048}, s[1] = {2048}; cuuint32_t b[2] = {64, 128}; enc(fn, &P.tmX, d_in[6], 2, d, s, b, S128, P128); }
  { cuuint64_t d[2] = {1024, 2048}, s[1] = {2048}; cuuint32_t b[2] = {64, 64}; enc(fn, &P.tmX0, d_in[6], 2, d, s, b, S128, P128); }
  { cuuint64_t d[3] = {1024, 1024, 3}, s[2] = {6144, 2048}; cuuint32_t b[3] = {64, 64, 3}; enc(fn, &P.tmW, d_in[7], 3, d, s, b, S128, P128); }
  { cuuint64_t d[4] = {64, 64, 16, 16}, s[3] = {2048, 131072, 128}; cuuint32_t b[4] = {64, 32, 2, 2}; enc(fn, &P.tmWo, d_in[8], 4, d, s, b, S128, P128); }
  { cuuint64_t d[4] = {64, 64, 16, 16}, s[3] = {2048, 131072, 128}; cuuint32_t b[4] = {64, 32, 2, 1}; enc(fn, &P.tmWo1, d_in[8], 4, d, s, b, S128, P128); }
  { cuuint64_t d[2] = {1024, 2048}, s[1] = {2048}; cuuint32_t b[2] = {16, 72}; enc(fn, &P.tmK, d_in[1], 2, d, s, b, S32, P128); }
  { cuuint64_t d[2] = {1024, 2048}, s[1] = {2048}; cuuint32_t b[2] = {16, 64}; enc(fn, &P.tmV, d_in[2], 2, d, s, b, S32, P128); }
  { cuuint64_t d[3] = {1024, 128, 16}, s[2] = {32768, 2048}; cuuint32_t b[3] = {16, 32, 2}; enc(fn, &P.tmQ, d_in[0], 3, d, s, b, S32, P128); }
  { cuuint64_t d[3] = {1024, 128, 16}, s[2] = {65536, 4096}; cuuint32_t b[3] = {16, 32, 2}; enc(fn, &P.tmOA, d_out, 3, d, s, b, S32, P0); }
  { cuuint64_t d[2] = {2048, 2048}, s[1] = {4096}; cuuint32_t b[2] = {64, 16}; enc(fn, &P.tmOB, d_out, 2, d, s, b, S128, P0); }
  cudaFuncSetAttribute(fused_kernel, cudaFuncAttributeMaxDynamicSharedMemorySize, SMEM_TOTAL);
  fused_kernel<<<128, 384, SMEM_TOTAL>>>(P);
}
```

```cpp
#include <cuda_runtime.h>
#include <cuda_bf16.h>
#include <cuda_fp16.h>
#include <cuda.h>
#include <stdint.h>

template<int TA, int TB, int SA=1> __device__ __forceinline__ void wgmma_ss_n192(float (&d)[96], uint64_t da, uint64_t db, int scale_d) {
  asm volatile("{\n.reg .pred p;\nsetp.ne.b32 p, %98, 0;\n"
    "wgmma.mma_async.sync.aligned.m64n192k16.f32.bf16.bf16 {%0, %1, %2, %3, %4, %5, %6, %7, %8, %9, %10, %11, %12, %13, %14, %15, %16, %17, %18, %19, %20, %21, %22, %23, %24, %25, %26, %27, %28, %29, %30, %31, %32, %33, %34, %35, %36, %37, %38, %39, %40, %41, %42, %43, %44, %45, %46, %47, %48, %49, %50, %51, %52, %53, %54, %55, %56, %57, %58, %59, %60, %61, %62, %63, %64, %65, %66, %67, %68, %69, %70, %71, %72, %73, %74, %75, %76, %77, %78, %79, %80, %81, %82, %83, %84, %85, %86, %87, %88, %89, %90, %91, %92, %93, %94, %95}, %96, %97, p, %101, 1, %99, %100;\n}\n"
    : "+f"(d[0]), "+f"(d[1]), "+f"(d[2]), "+f"(d[3]), "+f"(d[4]), "+f"(d[5]), "+f"(d[6]), "+f"(d[7]), "+f"(d[8]), "+f"(d[9]), "+f"(d[10]), "+f"(d[11]), "+f"(d[12]), "+f"(d[13]), "+f"(d[14]), "+f"(d[15]), "+f"(d[16]), "+f"(d[17]), "+f"(d[18]), "+f"(d[19]), "+f"(d[20]), "+f"(d[21]), "+f"(d[22]), "+f"(d[23]), "+f"(d[24]), "+f"(d[25]), "+f"(d[26]), "+f"(d[27]), "+f"(d[28]), "+f"(d[29]), "+f"(d[30]), "+f"(d[31]), "+f"(d[32]), "+f"(d[33]), "+f"(d[34]), "+f"(d[35]), "+f"(d[36]), "+f"(d[37]), "+f"(d[38]), "+f"(d[39]), "+f"(d[40]), "+f"(d[41]), "+f"(d[42]), "+f"(d[43]), "+f"(d[44]), "+f"(d[45]), "+f"(d[46]), "+f"(d[47]), "+f"(d[48]), "+f"(d[49]), "+f"(d[50]), "+f"(d[51]), "+f"(d[52]), "+f"(d[53]), "+f"(d[54]), "+f"(d[55]), "+f"(d[56]), "+f"(d[57]), "+f"(d[58]), "+f"(d[59]), "+f"(d[60]), "+f"(d[61]), "+f"(d[62]), "+f"(d[63]), "+f"(d[64]), "+f"(d[65]), "+f"(d[66]), "+f"(d[67]), "+f"(d[68]), "+f"(d[69]), "+f"(d[70]), "+f"(d[71]), "+f"(d[72]), "+f"(d[73]), "+f"(d[74]), "+f"(d[75]), "+f"(d[76]), "+f"(d[77]), "+f"(d[78]), "+f"(d[79]), "+f"(d[80]), "+f"(d[81]), "+f"(d[82]), "+f"(d[83]), "+f"(d[84]), "+f"(d[85]), "+f"(d[86]), "+f"(d[87]), "+f"(d[88]), "+f"(d[89]), "+f"(d[90]), "+f"(d[91]), "+f"(d[92]), "+f"(d[93]), "+f"(d[94]), "+f"(d[95])
    : "l"(da), "l"(db), "r"(scale_d), "n"(TA), "n"(TB), "n"(SA));
}
template<int TA, int TB, int SA=1> __device__ __forceinline__ void wgmma_ss_n128(float (&d)[64], uint64_t da, uint64_t db, int scale_d) {
  asm volatile("{\n.reg .pred p;\nsetp.ne.b32 p, %66, 0;\n"
    "wgmma.mma_async.sync.aligned.m64n128k16.f32.bf16.bf16 {%0, %1, %2, %3, %4, %5, %6, %7, %8, %9, %10, %11, %12, %13, %14, %15, %16, %17, %18, %19, %20, %21, %22, %23, %24, %25, %26, %27, %28, %29, %30, %31, %32, %33, %34, %35, %36, %37, %38, %39, %40, %41, %42, %43, %44, %45, %46, %47, %48, %49, %50, %51, %52, %53, %54, %55, %56, %57, %58, %59, %60, %61, %62, %63}, %64, %65, p, %69, 1, %67, %68;\n}\n"
    : "+f"(d[0]), "+f"(d[1]), "+f"(d[2]), "+f"(d[3]), "+f"(d[4]), "+f"(d[5]), "+f"(d[6]), "+f"(d[7]), "+f"(d[8]), "+f"(d[9]), "+f"(d[10]), "+f"(d[11]), "+f"(d[12]), "+f"(d[13]), "+f"(d[14]), "+f"(d[15]), "+f"(d[16]), "+f"(d[17]), "+f"(d[18]), "+f"(d[19]), "+f"(d[20]), "+f"(d[21]), "+f"(d[22]), "+f"(d[23]), "+f"(d[24]), "+f"(d[25]), "+f"(d[26]), "+f"(d[27]), "+f"(d[28]), "+f"(d[29]), "+f"(d[30]), "+f"(d[31]), "+f"(d[32]), "+f"(d[33]), "+f"(d[34]), "+f"(d[35]), "+f"(d[36]), "+f"(d[37]), "+f"(d[38]), "+f"(d[39]), "+f"(d[40]), "+f"(d[41]), "+f"(d[42]), "+f"(d[43]), "+f"(d[44]), "+f"(d[45]), "+f"(d[46]), "+f"(d[47]), "+f"(d[48]), "+f"(d[49]), "+f"(d[50]), "+f"(d[51]), "+f"(d[52]), "+f"(d[53]), "+f"(d[54]), "+f"(d[55]), "+f"(d[56]), "+f"(d[57]), "+f"(d[58]), "+f"(d[59]), "+f"(d[60]), "+f"(d[61]), "+f"(d[62]), "+f"(d[63])
    : "l"(da), "l"(db), "r"(scale_d), "n"(TA), "n"(TB), "n"(SA));
}
template<int TA, int TB, int SA=1> __device__ __forceinline__ void wgmma_ss_n72(float (&d)[36], uint64_t da, uint64_t db, int scale_d) {
  asm volatile("{\n.reg .pred p;\nsetp.ne.b32 p, %38, 0;\n"
    "wgmma.mma_async.sync.aligned.m64n72k16.f32.bf16.bf16 {%0, %1, %2, %3, %4, %5, %6, %7, %8, %9, %10, %11, %12, %13, %14, %15, %16, %17, %18, %19, %20, %21, %22, %23, %24, %25, %26, %27, %28, %29, %30, %31, %32, %33, %34, %35}, %36, %37, p, %41, 1, %39, %40;\n}\n"
    : "+f"(d[0]), "+f"(d[1]), "+f"(d[2]), "+f"(d[3]), "+f"(d[4]), "+f"(d[5]), "+f"(d[6]), "+f"(d[7]), "+f"(d[8]), "+f"(d[9]), "+f"(d[10]), "+f"(d[11]), "+f"(d[12]), "+f"(d[13]), "+f"(d[14]), "+f"(d[15]), "+f"(d[16]), "+f"(d[17]), "+f"(d[18]), "+f"(d[19]), "+f"(d[20]), "+f"(d[21]), "+f"(d[22]), "+f"(d[23]), "+f"(d[24]), "+f"(d[25]), "+f"(d[26]), "+f"(d[27]), "+f"(d[28]), "+f"(d[29]), "+f"(d[30]), "+f"(d[31]), "+f"(d[32]), "+f"(d[33]), "+f"(d[34]), "+f"(d[35])
    : "l"(da), "l"(db), "r"(scale_d), "n"(TA), "n"(TB), "n"(SA));
}
template<int TB, int SA=1> __device__ __forceinline__ void wgmma_rs_n40(float (&d)[20], uint32_t a0, uint32_t a1, uint32_t a2, uint32_t a3, uint64_t db, int scale_d) {
  asm volatile("{\n.reg .pred p;\nsetp.ne.b32 p, %25, 0;\n"
    "wgmma.mma_async.sync.aligned.m64n40k16.f32.bf16.bf16 {%0, %1, %2, %3, %4, %5, %6, %7, %8, %9, %10, %11, %12, %13, %14, %15, %16, %17, %18, %19}, {%20, %21, %22, %23}, %24, p, %27, 1, %26;\n}\n"
    : "+f"(d[0]), "+f"(d[1]), "+f"(d[2]), "+f"(d[3]), "+f"(d[4]), "+f"(d[5]), "+f"(d[6]), "+f"(d[7]), "+f"(d[8]), "+f"(d[9]), "+f"(d[10]), "+f"(d[11]), "+f"(d[12]), "+f"(d[13]), "+f"(d[14]), "+f"(d[15]), "+f"(d[16]), "+f"(d[17]), "+f"(d[18]), "+f"(d[19])
    : "r"(a0), "r"(a1), "r"(a2), "r"(a3), "l"(db), "r"(scale_d), "n"(TB), "n"(SA));
}
template<int TB> __device__ __forceinline__ void wgmma_hrs_n64(uint32_t (&d)[16], uint32_t a0, uint32_t a1, uint32_t a2, uint32_t a3, uint64_t db, int scale_d) {
  asm volatile("{\n.reg .pred p;\nsetp.ne.b32 p, %21, 0;\n"
    "wgmma.mma_async.sync.aligned.m64n64k16.f16.f16.f16 {%0, %1, %2, %3, %4, %5, %6, %7, %8, %9, %10, %11, %12, %13, %14, %15}, {%16, %17, %18, %19}, %20, p, 1, 1, %22;\n}\n"
    : "+r"(d[0]), "+r"(d[1]), "+r"(d[2]), "+r"(d[3]), "+r"(d[4]), "+r"(d[5]), "+r"(d[6]), "+r"(d[7]), "+r"(d[8]), "+r"(d[9]), "+r"(d[10]), "+r"(d[11]), "+r"(d[12]), "+r"(d[13]), "+r"(d[14]), "+r"(d[15])
    : "r"(a0), "r"(a1), "r"(a2), "r"(a3), "l"(db), "r"(scale_d), "n"(TB));
}
template<int TB> __device__ __forceinline__ void wgmma_hrs_n32(uint32_t (&d)[8], uint32_t a0, uint32_t a1, uint32_t a2, uint32_t a3, uint64_t db, int scale_d) {
  asm volatile("{\n.reg .pred p;\nsetp.ne.b32 p, %13, 0;\n"
    "wgmma.mma_async.sync.aligned.m64n32k16.f16.f16.f16 {%0, %1, %2, %3, %4, %5, %6, %7}, {%8, %9, %10, %11}, %12, p, 1, 1, %14;\n}\n"
    : "+r"(d[0]), "+r"(d[1]), "+r"(d[2]), "+r"(d[3]), "+r"(d[4]), "+r"(d[5]), "+r"(d[6]), "+r"(d[7])
    : "r"(a0), "r"(a1), "r"(a2), "r"(a3), "l"(db), "r"(scale_d), "n"(TB));
}

__device__ __align__(128) const uint32_t c_thr[1536] = {
  0x33fb33ff,0xa49c9de4,0x33273352,0xaf2cae76,0x33e233f1,0xa96ca7bd,0x32c432f7,0xb045afdd,0x33b733cf,0xac3eaaf7,0x3250328c,0xb0eab099,
  0x3378339a,0xadbcacff,0x31cd3211,0xb182b137,0x33d033fb,0xaadea46a,0x299e2d17,0xb3e0b396,0x32fb337a,0xafd2adb1,0xa78b1f76,0xb3f2b3ff,
  0x318b3254,0xb1c5b0e5,0xae6bac32,0xb354b3b8,0x2f4230a3,0xb321b285,0xb133b040,0xb215b2c7,0x337c33f2,0xada5a759,0xb179afc8,0xb1d6b2fe,
  0x31463293,0xb204b08e,0xb394b2ba,0xad23b055,0x2b402f4e,0xb3cbb31e,0xb3e4b3f9,0x293ba533,0xac269c52,0xb3bab400,0xb258b357,0x30e02e5f,
  0x330133e5,0xafbda922,0xb3f3b3c9,0x2727ab59,0x2deb314a,0xb36fb200,0xb194b32f,0x31bc2f0a,0xacdb2084,0xb39fb3ff,0xa565aea4,0x33f93347,
  0xb2b6b0db,0xb05ab25c,0x30892c1a,0x329733bc,0x326033d4,0xb0d6aa94,0xb00ab29b,0x32e83084,0x20e82f64,0xb3feb318,0x2d8da597,0x338133f8,
  0xb1fcae48,0xb14fb35c,0x339031b8,0x2d3a3199,0xb3e6b3ae,0x2909ac7b,0x32d133f4,0xb030a6f5,0x319d33bf,0xb1b3ac02,0x2e3ca874,0x335e33ec,
  0xacc32b89,0xb3a3b3c6,0x33f83276,0x25c930b7,0xb3dcb1f8,0xaa01b154,0x30653335,0xb2b0aef4,0xb107b383,0x32392d81,0xafa6214d,0xb307b3fe,
  0x30bc33a5,0xb273acb7,0x33c5311b,0x2ba23229,0xb0cc94b6,0xb267b400,0x30153360,0xb2e1ae31,0xb385b3ab,0x2d76ac93,0xb166a691,0xb1e7b3f5,
  0x22deb06a,0x33fd32ac,0xb337b3da,0x2ee8aa19,0x2f853387,0xb310ad6a,0x322d33fe,0xb1162216,0xb2a9abd3,0xb06fb3c2,0xb07428a6,0xb2a5b3ea,
  0xb111b3e9,0x323128be,0xb30db3c3,0x2f90abba,0x31aa227a,0x31a633fd,0x2e25ad5e,0x33633389,0x2d6a3365,0xb387ae1a,0xa21631aa,0xb3feb1a6,
  0xb3c2af85,0xabd3b310,0xb3eab22d,0x28a6b116,0xa8beb2a9,0x33e9306f,0x2bbab074,0x33c332a5,0x33fd3111,0x227a3231,0x3389330d,0xad5e2f90,
  0x2a63333f,0xb3d7aec6,0xb2a2a1b1,0xb07ab3fe,0xb3f7b158,0x25fbb1f4,0xacb7b38b,0x33a52d52,0x2e0eb025,0x336832d8,0x340030bc,0x14b63273,
  0x323533c0,0xb10c2beb,0xac9330cc,0xb3abb267,0x23433316,0xb3fdaf6f,0xb38eb225,0x2d46b11f,0xb342b29e,0x2ebbb07f,0x31e3aa7c,0x316b33d6,
  0x3264a6c3,0x30d133f5,0x2c0233ac,0xb3bfac87,0x28f0336a,0xb3e7ae02,0xb3c6b19d,0x2b89b1b3,0xa59732e8,0xb3f8b00a,0xaccfb3ed,0x33a1285b,
  0xb1b8b381,0x3199ad8d,0x336c31df,0xadf73170,0x33f42d3a,0x26f53390,0xb30423a7,0xafb2b3fc,0xb05f3030,0xb2b3b2d1,0x29e8b27a,0x33dd30b2,
  0xab5932b6,0xb3c9b05a,0x30adb089,0x327e3297,0xaf0ab3f3,0x332fa727,0x240633b0,0xb3fcac6f,0x33473194,0xaea431bc,0xb174b359,0x31daae54,
  0xb3bca565,0xac1ab3f9,0x33ee2f59,0xa842331b,0xaddf3281,0xb371b0a8,0x34002b40,0x1c5233cb,0xa759b3ef,0x33f22829,0xb2fe2c26,0xafc8b3ba,
  0x308e337c,0xb2932da5,0x3055b179,0x32ba31d6,0xb31eb146,0x2f4eb204,0xa5333394,0xb3f9ad23,0xaff33249,0xb2f1b0f3,0x30e532fb,0xb2542fd2,
  0x2b28b373,0x33cc2dd4,0xb285b18b,0x30a3b1c5,0x246a33fa,0xb3fba500,0x33962f42,0xad173321,0xadb1b3d0,0x337aaade,0xb3ffa99e,0x1f76b3e0,
  0xb0ee320d,0xb24db13c,0xac4b3398,0xb3b5ad0b,0x304ab289,0x32c1309e,0x2985b3ce,0x33e12b0f,0xaf3732f4,0xb324afe8,0xa4ce33f0,0xb3faa7ef,
  0x2dc8b34f,0x33762e82,0x9de4b3ff,0x33ff1ead,0xb1c931cd,0xb186b182,0xb3762e82,0xadc8b34f,0x324db13c,0x30ee320d,0x33b5ad0b,0x2c4b3398,
  0xb2c1309e,0xb04ab289,0xb3e12b0f,0xa985b3ce,0x3324afe8,0x2f3732f4,0x33faa7ef,0x24ce33f0,0xb285318b,0xb0a3b1c5,0xb2c7ae6b,0x3040b354,
  0x3396af42,0x2d173321,0x31413133,0xb2093215,0xb3ff299e,0x9f76b3e0,0xae8db2bd,0x334cb050,0x33b8278b,0xac3233f2,0x281033b3,0xb3ef2c57,
  0xb31e3146,0xaf4eb204,0xa533b394,0x33f9ad23,0x3400ab40,0x9c5233cb,0xae5f33e4,0xb357a93b,0xb2feac26,0x2fc8b3ba,0x3245b258,0x30f830e0,
  0x30553179,0xb2ba31d6,0xb3df2e99,0xa9b6b34a,0xb39230fd,0xad2fb241,0x3200b301,0x314a2fbd,0x337f1b11,0xad993400,0xb3ff2deb,0xa084b36f,
  0xb005b129,0x32ebb21d,0x325c2cdb,0xb0db339f,0xa92233de,0xb3e529cf,0xab59b2b6,0x33c9b05a,0xb3dd30b2,0xa9e8b27a,0x33d4ab71,0xaa9433c8,
  0x32212c0e,0xb12433bd,0xaf64b0d6,0x3318b260,0x197fb345,0x3400aeaf,0xae4833fe,0xb35c20e8,0xb23d3332,0xb102aeff,0x33aeb14f,0x2c7b31fc,
  0xb3fe3065,0xa14db2b0,0x2ebb307f,0xb342329e,0x300f2fa6,0xb2e53307,0x30d1b3f5,0x326426c3,0x302ab400,0x32d517db,0xb3e72e02,0x28f0b36a,
  0xb3fd2f6f,0x2343b316,0x2d46311f,0xb38e3225,0xb3f53015,0x2691b2e1,0xaf9b33eb,0xb30a288d,0x2a193166,0xb3da31e7,0x33d7aec6,0xaa63333f,
  0x3313b337,0x2f7a2ee8,0xa5fbb1f4,0x33f7b158,0xb1a1a8d7,0x31afb3e8,0xb36832d8,0xae0eb025,0xb3c22f85,0x2bd3b310,0xb3ea322d,0xa8a6b116,
  0xa8be32a9,0xb3e9306f,0x2bba3074,0xb3c332a5,0x33fdb111,0xa27a3231,0x3389b30d,0x2d5e2f90,0xa216b1aa,0x33feb1a6,0xaed2ae25,0x333db363,
  0xb3652edd,0x2e1ab33a,0xb1aa227a,0x31a6b3fd,0xaf853387,0xb3102d6a,0xb22d33fe,0xb116a216,0x32a9abd3,0xb06f33c2,0x307428a6,0xb2a533ea,
  0x3111b3e9,0x3231a8be,0x330db3c3,0x2f902bba,0xb2e12e31,0x3015b360,0x288db1a1,0x33ebb1af,0xb1e733f5,0xb1662691,0xb33f2f9b,0x2ec6b30a,
  0x2ee82a19,0xb33733da,0xb15833d7,0xb1f42a63,0x33e8b313,0x28d72f7a,0x302525fb,0xb2d833f7,0xb2392d81,0x3107b383,0x3307b3fe,0x2fa6214d,
  0xb35e33ec,0xae3ca874,0x97dbb00f,0x3400b2e5,0xa5c930b7,0xb3f83276,0xb316302a,0x2f6fb2d5,0x32b0aef4,0xb0653335,0xb29e33fd,0xb07f2343,
  0xb1702ccf,0x31dfb3a1,0x3345b124,0xaeaf3221,0xb3fc336c,0xa3a7adf7,0x3332b400,0x2eff997f,0xb0b23304,0xb27a2fb2,0x2b71b102,0x33c8b23d,
  0x2c0e29e8,0xb3bd33dd,0xb0d62a94,0x3260b3d4,0xb0892c1a,0x3297b3bc,0x2aad2842,0xb3d333ee,0xb3b0327e,0x2c6fb0ad,0x3241b035,0xb0fd32ce,
  0xb35933fc,0xae542406,0x3400b392,0x1b112d2f,0xaf5931da,0xb31b3174,0x321db37f,0x3129ad99,0xaf152ac6,0x332cb3d2,0xb1463293,0xb204308e,
  0xb281312e,0x30a8b219,0xab402f4e,0xb3cb331e,0xb3ef3371,0x2829addf,0x2c269c52,0xb3ba3400,0xb37c33f2,0xada52759,0x3179afc8,0xb1d632fe,
  0xacf32953,0x339cb3e3,0xb3fa33cc,0x2500ab28,0xb0942f21,0x3290b32a,0xb3d033fb,0xaade246a,0xb249317d,0x30f3b1d2,0xb2fb337a,0xafd22db1,
  0xb37332f1,0x2dd4aff3,0xb18b3254,0xb1c530e5,0xa96c27bd,0x33e2b3f1,0xb0452fdd,0x32c4b2f7,0xac3e2af7,0x33b7b3cf,0xb0ea3099,0x3250b28c,
  0xadbc2cff,0x3378b39a,0xb1823137,0x31cdb211,0xaf2c2e76,0x3327b352,0xb20d31c9,0x313cb186,0x313c3186,0xb20db1c9,0x2d0b2dc8,0xb398b376,
  0x309e30ee,0xb289b24d,0x2b0f2c4b,0xb3ceb3b5,0x2fe8304a,0xb2f4b2c1,0x27ef2985,0xb3f0b3e1,0x2e822f37,0xb34fb324,0x1ead24ce,0xb3ffb3fa,
  0xb2bdb209,0xb050b141,0xb290b32a,0x30942f21,0xb3b3b34c,0xac57ae8d,0xb0f3b1d2,0x3249317d,0xb400b3ef,0x1d1ba810,0xadd4aff3,0x337332f1,
  0xb39cb3e3,0x2cf32953,0xa500ab28,0x33fa33cc,0xae99b0f8,0x334a3245,0x33ff33b2,0x201f2c63,0x2438a9b6,0x33fc33df,0x332c33d2,0xaf15aac6,
  0x303a2ce7,0x32cb339e,0x30a83219,0xb281b12e,0x32ee31c0,0x2ffe3190,0x28292ddf,0xb3efb371,0x33b0327e,0x2c6f30ad,0xb241b035,0xb0fdb2ce,
  0x335933fc,0xae54a406,0xb400b392,0x1b11ad2f,0x2f5931da,0xb31bb174,0xb21db37f,0x31292d99,0xaaad2842,0xb3d3b3ee,0xa9cfb005,0x33de32eb,
  0x285b305f,0xb3edb2b3,0x2c0ea9e8,0x33bd33dd,0xb170accf,0xb1dfb3a1,0x33453124,0x2eaf3221,0xb3fcb36c,0x23a7adf7,0x33323400,0xaeff997f,
  0xb0b2b304,0x327a2fb2,0x2b713102,0xb3c8b23d,0xb400b2e5,0x17dbb00f,0x2e023264,0xb36ab0d1,0xaf6fb2d5,0x3316302a,0xb11fa8f0,0xb225b3e7,
  0x307f2343,0x329e33fd,0xb3d6b38e,0x2a7cad46,0x33f53342,0xa6c32ebb,0xac87b1e3,0x33ac316b,0x28d7af7a,0x33e83313,0xb2d8b3f7,0x3025a5fb,
  0x33eb31af,0x288d31a1,0x2bebae0e,0x33c03368,0x2ec6330a,0xb33faf9b,0x33fe3235,0x21b1310c,0xb1f4aa63,0xb158b3d7,0x2d5232a2,0xb38bb07a,
  0x33a7333d,0xacab2ed2,0x33f63162,0x262d31eb,0xaa4b301a,0xb3d8b2de,0x2a32326b,0xb3d9b0c7,0xb3f6b26f,0x265fb0c1,0xb3a9b020,0xac9fb2db,
  0x0e48b15d,0x340031f0,0xae1ab33a,0x33652edd,0xaed22e25,0xb33db363,0xb1eb0e48,0xb162b400,0xb2deb3a7,0x301aacab,0xb0c7b3f6,0x326b262d,
  0x30c1aa4b,0x326f33d8,0x32db2a32,0x302033d9,0x31f033f6,0xb15d265f,0x2edd33a9,0xb33aac9f,0xb2acb385,0x306aad76,0x2a19b166,0x33da31e7,
  0x3229a2de,0x311b33fd,0x33133337,0xaf7a2ee8,0x2e3133c5,0xb360aba2,0xb1a128d7,0xb1afb3e8,0xb3f5b015,0xa691b2e1,0xaf9bb3eb,0x330a288d,
  0x3154acc3,0x31f833a3,0x2ef433f8,0xb335a5c9,0x2d8133dc,0xb383aa01,0xb3feb065,0x214db2b0,0xb3ecb107,0x2874b239,0x300fafa6,0x32e53307,
  0x30b7ae3c,0x3276335e,0x302a3400,0xb2d517db,0x312433bd,0xb2212c0e,0xb318b260,0x2f64b0d6,0xb400aeaf,0x997fb345,0x335c20e8,0x2e4833fe,
  0x3102aeff,0x323d3332,0xac7b31fc,0xb3aeb14f,0x2a9433c8,0xb3d4ab71,0xb084b3e6,0x329ba909,0xb2ce2aad,0xb035b3d3,0x33e529cf,0x292233de,
  0x2d2fb241,0x339230fd,0xb14a2fbd,0xb200b301,0x2d993400,0xb37f1b11,0x2084b36f,0x33ff2deb,0xb2ebb21d,0x3005b129,0x30db339f,0xb25c2cdb,
  0xae5fb3e4,0x3357a93b,0xb190303a,0xb1c0b2cb,0x32453258,0xb0f830e0,0x2c63b2ee,0x33b22ffe,0xb3dfae99,0x29b6b34a,0x2ac633ff,0xb3d2a01f,
  0x339ea438,0x2ce733fc,0xb12eb32c,0x3219af15,0x33b8a78b,0x2c3233f2,0x2810b3b3,0x33ef2c57,0xb2c72e6b,0xb040b354,0x29533400,0xb3e31d1b,
  0x3141b133,0x32093215,0xaf21b39c,0x332aacf3,0xae8d32bd,0xb34cb050,0x317d3290,0xb1d23094,0x27bd33fb,0xb3f1249c,0x2fdd3327,0xb2f72f2c,
  0xaaf7b3e2,0x33cfa96c,0xb099b2c4,0x328cb045,0x2cff33b7,0xb39a2c3e,0x31373250,0xb21130ea,0xae76b378,0x3352adbc,0xb1c9b1cd,0x3186b182,
  0xb3ff1ead,0x1de4b3ff,0xb352adbc,0x2e76b378,0x33f1249c,0xa7bd33fb,0x32f72f2c,0xafdd3327,0xb3cfa96c,0x2af7b3e2,0xb28cb045,0x3099b2c4,
  0x339a2c3e,0xacff33b7,0x321130ea,0xb1373250,0x2953b400,0x33e31d1b,0x33ccadd4,0x2b283373,0xaf21339c,0xb32aacf3,0xb3fb2500,0x246ab3fa,
  0x317db290,0x31d23094,0x337a2ade,0xadb133d0,0xb2f130f3,0xaff3b249,0xb254afd2,0x30e5b2fb,0x339e2438,0xace733fc,0xb12e332c,0xb219af15,
  0xb190b03a,0x31c0b2cb,0x3371b0a8,0x2ddf3281,0x2c6332ee,0xb3b22ffe,0xb3f22829,0x2759b3ef,0x2ac6b3ff,0x33d2a01f,0x32932da5,0xb08e337c,
  0xaf0a33f3,0xb32fa727,0x2406b3b0,0x33fcac6f,0x3347b194,0x2ea431bc,0xb1743359,0xb1daae54,0xb3bc2565,0x2c1ab3f9,0x33eeaf59,0x2842331b,
  0x30ad3089,0xb27e3297,0xb2ceaaad,0x3035b3d3,0xb29ba909,0x3084b3e6,0x305f3030,0xb2b332d1,0x259732e8,0xb3f8300a,0x2ccfb3ed,0x33a1a85b,
  0x31b8b381,0x31992d8d,0xb36c31df,0xadf7b170,0xb3f42d3a,0x26f5b390,0x330423a7,0xafb233fc,0x316bb3d6,0x31e32a7c,0xb3832a01,0x2d81b3dc,
  0xb3bf2c87,0x2c02b3ac,0x28743239,0xb3ec3107,0x2b8931b3,0xb3c6319d,0x3276b35e,0x30b72e3c,0x31f8b3a3,0x31542cc3,0xb33525c9,0x2ef4b3f8,
  0x310c2beb,0xb23533c0,0x33abb267,0x2c9330cc,0x307ab3fe,0x32a2a1b1,0xb06aad76,0x32acb385,0xb3a52d52,0x2cb7b38b,0xb11b33fd,0xb229a2de,
  0x94b63273,0xb40030bc,0x3360aba2,0xae3133c5,0xb2de33a7,0xb01aacab,0xb0c733f6,0xb26b262d,0x30c12a4b,0xb26f33d8,0x32dbaa32,0xb02033d9,
  0x31f0b3f6,0x315d265f,0x2eddb3a9,0x333aac9f,0xb1eb8e48,0x3162b400,0xb3872e1a,0x2d6ab365,0xae25ad5e,0x3363b389,0x8e48b15d,0x3400b1f0,
  0xb3a7333d,0xacabaed2,0xb3f63162,0x262db1eb,0x2a4b301a,0xb3d832de,0xaa32326b,0xb3d930c7,0x33f6b26f,0x265f30c1,0x33a9b020,0xac9f32db,
  0x33c0b368,0x2beb2e0e,0x30cc94b6,0xb2673400,0x21b1b10c,0x33feb235,0x3385b3ab,0x2d762c93,0xb38b307a,0x2d52b2a2,0xa2deb06a,0x33fdb2ac,
  0xb0bc33a5,0xb2732cb7,0xb3c5311b,0x2ba2b229,0x26c32ebb,0xb3f53342,0xb3ac316b,0x2c87b1e3,0x336ab0d1,0xae023264,0xb19d33bf,0xb1b32c02,
  0x3225b3e7,0x311fa8f0,0x2cc32b89,0xb3a333c6,0xaa7cad46,0x33d6b38e,0x33dcb1f8,0xaa013154,0xb3fe3318,0x20e8af64,0x3381b3f8,0x2d8d2597,
  0xb14f335c,0xb1fc2e48,0x2d3ab199,0x3390b1b8,0x29092c7b,0xb3e633ae,0xb03026f5,0x32d1b3f4,0x32e8b084,0xb00a329b,0xb3ed32b3,0x285bb05f,
  0x29cfb005,0x33deb2eb,0xb05a325c,0xb2b630db,0xafbd2922,0x3301b3e5,0x27272b59,0xb3f333c9,0xb36f3200,0x2debb14a,0x31bcaf0a,0xb194332f,
  0xb39f33ff,0xacdba084,0x33f9b347,0xa5652ea4,0x3394b2ba,0xad233055,0xa438a9b6,0x33fcb3df,0x33e4b3f9,0x293b2533,0xb03a2ce7,0x32cbb39e,
  0x3258b357,0x30e0ae5f,0xb2ee31c0,0x2ffeb190,0x2e99b0f8,0x334ab245,0xb3ff33b2,0x201fac63,0xaf4230a3,0xb3213285,0x3133b040,0xb21532c7,
  0xa99e2d17,0xb3e03396,0x32bdb209,0xb0503141,0x278b1f76,0xb3f233ff,0x33b3b34c,0xac572e8d,0x2e6bac32,0xb35433b8,0x3400b3ef,0x1d1b2810,
  0xb289324d,0x309eb0ee,0xb3ce33b5,0x2b0fac4b,0xb2f432c1,0x2fe8b04a,0xb3f033e1,0x27efa985,0xb34f3324,0x2e82af37,0xb3ff33fa,0x1eada4ce,
  0xb3983376,0x2d0badc8,0xb3fb33ff,0xa49c1de4,0x351c35f6,0xac93a617,0xb8a3b93c,0x308d2a16,0x32f43448,0xb160afa5,0xb6a4b7fe,0x353a3389,
  0x2fa53160,0xb448b2f4,0xb389b53a,0x37fe36a4,0x26172c93,0xb5f6b51c,0xaa16b08d,0x393c38a3,0x34c3358c,0xac47a5b2,0xb85fb8f3,0x304229b1,
  0x327e33fd,0xb106af26,0xb63cb785,0x34e7330f,0x2f263106,0xb3fdb27e,0xb30fb4e7,0x3785363c,0x25b22c47,0xb58cb4c3,0xa9b1b042,0x38f3385f,
  0x346a3523,0xabf6a54d,0xb81ab8a8,0x2fef294d,0x3209336b,0xb0acaea7,0xb5d4b70a,0x34933294,0x2ea730ac,0xb36bb209,0xb294b493,0x370a35d4,
  0x254d2bf6,0xb523b46a,0xa94dafef,0x38a8381a,0x341334bc,0xab5fa4e9,0xb7a6b85a,0x2f5928e8,0x319432da,0xb052ae28,0xb56ab68d,0x343e3219,
  0x2e283052,0xb2dab194,0xb219b43e,0x368d356a,0x24e92b5f,0xb4bcb413,0xa8e8af59,0x385a37a6,0x33783456,0xaac8a484,0xb715b80a,0x2ec32884,
  0x3120324a,0xaff2ada9,0xb4ffb60e,0x33d3319e,0x2da92ff2,0xb24ab120,0xb19eb3d3,0x360e34ff,0x24842ac8,0xb456b378,0xa884aec3,0x380a3715,
  0x32cd33e3,0xaa31a420,0xb682b76f,0x2e2d281f,0x30ac31bb,0xaf3fad2a,0xb493b58d,0x33283122,0x2d2a2f3f,0xb1bbb0ac,0xb122b328,0x358d3493,
  0x24202a31,0xb3e3b2cd,0xa81fae2d,0x376f3682,0x3223331c,0xa999a376,0xb5ebb6c6,0x2d972776,0x3039312d,0xae8dacac,0xb426b50b,0x327c30a6,
  0x2cac2e8d,0xb12db039,0xb0a6b27c,0x350b3426,0x23762999,0xb31cb223,0xa776ad97,0x36c635eb,0x317a3257,0xa902a2ad,0xb552b61a,0x2d0026ad,
  0x2f8c309f,0xaddcac2e,0xb371b487,0x31cf3029,0x2c2e2ddc,0xb09faf8c,0xb029b1cf,0x34873371,0x22ad2902,0xb257b17a,0xa6adad00,0x361a3552,
  0x30d23194,0xa86ba1e4,0xb4b7b56a,0x2c6a25e4,0x2ea73012,0xad2aab5f,0xb294b402,0x31222f59,0x2b5f2d2a,0xb012aea7,0xaf59b122,0x34023294,
  0x21e4286b,0xb194b0d2,0xa5e4ac6a,0x356a34b7,0x302c30d2,0xa7a9a11b,0xb41ab4b7,0x2ba7251b,0x2dc22f0c,0xac79aa63,0xb1b6b2f7,0x30742e5f,
  0x2a632c79,0xaf0cadc2,0xae5fb074,0x32f731b6,0x211b27a9,0xb0d2b02c,0xa51baba7,0x34b7341a,0x2f0c3012,0xa67ba052,0xb2f7b402,0x2a7a2452,
  0x2cde2df5,0xab91a967,0xb0d7b1e8,0x2f8b2d65,0x29672b91,0xadf5acde,0xad65af8b,0x31e830d7,0x2052267b,0xb012af0c,0xa452aa7a,0x340232f7,
  0x2dc22ea7,0xa54d9f12,0xb1b6b294,0x294d2311,0x2bf62cde,0xaa31a86b,0xafefb0d7,0x2e2d2c6a,0x286b2a31,0xacdeabf6,0xac6aae2d,0x30d72fef,
  0x1f12254d,0xaea7adc2,0xa311a94d,0x329431b6,0x2c792d2a,0xa4209d7f,0xb074b122,0x281f217f,0x2a312b91,0xa8d0a6e0,0xae2daf8b,0x2cce2ade,
  0x26e028d0,0xab91aa31,0xaadeacce,0x2f8b2e2d,0x1d7f2420,0xad2aac79,0xa17fa81f,0x31223074,0x2a632b5f,0xa1e49bdb,0xae5faf59,0x25e41fdb,
  0x286b2967,0xa6e0a4e9,0xac6aad65,0x2ade28e8,0x24e926e0,0xa967a86b,0xa8e8aade,0x2d652c6a,0x1bdb21e4,0xab5faa63,0x9fdba5e4,0x2f592e5f,
  0x27a9286b,0x9f1298b6,0xaba7ac6a,0x23111cb6,0x254d267b,0xa420a1e4,0xa94daa7a,0x281f25e4,0x21e42420,0xa67ba54d,0xa5e4a81f,0x2a7a294d,
  0x18b61f12,0xa86ba7a9,0x9cb6a311,0x2c6a2ba7,0x211b21e4,0x98b69248,0xa51ba5e4,0x1cb61648,0x1f122052,0x9d7f9bdb,0xa311a452,0x217f1fdb,
  0x1bdb1d7f,0xa0529f12,0x9fdba17f,0x24522311,0x124818b6,0xa1e4a11b,0x96489cb6,0x25e4251b,0xa11ba1e4,0x18b61248,0x251b25e4,0x9cb69648,
  0x9f12a052,0x1d7f1bdb,0x23112452,0xa17f9fdb,0x9bdb9d7f,0x20521f12,0x1fdb217f,0xa452a311,0x924898b6,0x21e4211b,0x16481cb6,0xa5e4a51b,
  0xa7a9a86b,0x1f1218b6,0x2ba72c6a,0xa3119cb6,0xa54da67b,0x242021e4,0x294d2a7a,0xa81fa5e4,0xa1e4a420,0x267b254d,0x25e4281f,0xaa7aa94d,
  0x98b69f12,0x286b27a9,0x1cb62311,0xac6aaba7,0xaa63ab5f,0x21e41bdb,0x2e5f2f59,0xa5e49fdb,0xa86ba967,0x26e024e9,0x2c6a2d65,0xaadea8e8,
  0xa4e9a6e0,0x2967286b,0x28e82ade,0xad65ac6a,0x9bdba1e4,0x2b5f2a63,0x1fdb25e4,0xaf59ae5f,0xac79ad2a,0x24201d7f,0x30743122,0xa81fa17f,
  0xaa31ab91,0x28d026e0,0x2e2d2f8b,0xacceaade,0xa6e0a8d0,0x2b912a31,0x2ade2cce,0xaf8bae2d,0x9d7fa420,0x2d2a2c79,0x217f281f,0xb122b074,
  0xadc2aea7,0x254d1f12,0x31b63294,0xa94da311,0xabf6acde,0x2a31286b,0x2fef30d7,0xae2dac6a,0xa86baa31,0x2cde2bf6,0x2c6a2e2d,0xb0d7afef,
  0x9f12a54d,0x2ea72dc2,0x2311294d,0xb294b1b6,0xaf0cb012,0x267b2052,0x32f73402,0xaa7aa452,0xacdeadf5,0x2b912967,0x30d731e8,0xaf8bad65,
  0xa967ab91,0x2df52cde,0x2d652f8b,0xb1e8b0d7,0xa052a67b,0x30122f0c,0x24522a7a,0xb402b2f7,0xb02cb0d2,0x27a9211b,0x341a34b7,0xaba7a51b,
  0xadc2af0c,0x2c792a63,0x31b632f7,0xb074ae5f,0xaa63ac79,0x2f0c2dc2,0x2e5f3074,0xb2f7b1b6,0xa11ba7a9,0x30d2302c,0x251b2ba7,0xb4b7b41a,
  0xb0d2b194,0x286b21e4,0x34b7356a,0xac6aa5e4,0xaea7b012,0x2d2a2b5f,0x32943402,0xb122af59,0xab5fad2a,0x30122ea7,0x2f593122,0xb402b294,
  0xa1e4a86b,0x319430d2,0x25e42c6a,0xb56ab4b7,0xb17ab257,0x290222ad,0x3552361a,0xad00a6ad,0xaf8cb09f,0x2ddc2c2e,0x33713487,0xb1cfb029,
  0xac2eaddc,0x309f2f8c,0x302931cf,0xb487b371,0xa2ada902,0x3257317a,0x26ad2d00,0xb61ab552,0xb223b31c,0x29992376,0x35eb36c6,0xad97a776,
  0xb039b12d,0x2e8d2cac,0x3426350b,0xb27cb0a6,0xacacae8d,0x312d3039,0x30a6327c,0xb50bb426,0xa376a999,0x331c3223,0x27762d97,0xb6c6b5eb,
  0xb2cdb3e3,0x2a312420,0x3682376f,0xae2da81f,0xb0acb1bb,0x2f3f2d2a,0x3493358d,0xb328b122,0xad2aaf3f,0x31bb30ac,0x31223328,0xb58db493,
  0xa420aa31,0x33e332cd,0x281f2e2d,0xb76fb682,0xb378b456,0x2ac82484,0x3715380a,0xaec3a884,0xb120b24a,0x2ff22da9,0x34ff360e,0xb3d3b19e,
  0xada9aff2,0x324a3120,0x319e33d3,0xb60eb4ff,0xa484aac8,0x34563378,0x28842ec3,0xb80ab715,0xb413b4bc,0x2b5f24e9,0x37a6385a,0xaf59a8e8,
  0xb194b2da,0x30522e28,0x356a368d,0xb43eb219,0xae28b052,0x32da3194,0x3219343e,0xb68db56a,0xa4e9ab5f,0x34bc3413,0x28e82f59,0xb85ab7a6,
  0xb46ab523,0x2bf6254d,0x381a38a8,0xafefa94d,0xb209b36b,0x30ac2ea7,0x35d4370a,0xb493b294,0xaea7b0ac,0x336b3209,0x32943493,0xb70ab5d4,
  0xa54dabf6,0x3523346a,0x294d2fef,0xb8a8b81a,0xb4c3b58c,0x2c4725b2,0x385f38f3,0xb042a9b1,0xb27eb3fd,0x31062f26,0x363c3785,0xb4e7b30f,
  0xaf26b106,0x33fd327e,0x330f34e7,0xb785b63c,0xa5b2ac47,0x358c34c3,0x29b13042,0xb8f3b85f,0xb51cb5f6,0x2c932617,0x38a3393c,0xb08daa16,
  0xb2f4b448,0x31602fa5,0x36a437fe,0xb53ab389,0xafa5b160,0x344832f4,0x3389353a,0xb7feb6a4,0xa617ac93,0x35f6351c,0x2a16308d,0xb93cb8a3,
};
__device__ __align__(128) const uint32_t c_img[2560] = {
  0x326d31ed,0x333b32dd,0x33c33388,0x33fe33ea,0x33c331ed,0x31ed33c3,0xa8b22d64,0xb33bb0c4,0x33ea31ed,0xad64301d,0xb2ddb388,0x315fa8b2,
  0x32dd31ed,0xb3feabc6,0x326dad64,0xad64326d,0x30c431ed,0xaed7b2dd,0x2bc63388,0xa248b3ea,0x2bc631ed,0x315fb3c3,0xb3ea2d64,0x2ed730c4,
  0xa8b231ed,0x3388b01d,0x301db388,0xb1ed28b2,0xb01d31ed,0x22482bc6,0x30c4ad64,0x3388b26d,0x33ea33fe,0x338833c3,0x32dd333b,0x31ed326d,
  0xb2ddb3fe,0xa248b01d,0x326d2ed7,0x338833ea,0x30c433fe,0xb33babc6,0xabc6b33b,0x33fe30c4,0xabc6b3fe,0x31ed32dd,0xb3eaaed7,0x333ba8b2,
  0xa8b233fe,0x2d64b3c3,0xb01d333b,0x315fb26d,0x301db3fe,0xb3fe301d,0x30c42ed7,0x2d64b3ea,0xb26d33fe,0x2ed72bc6,0x33c3b33b,0xa248b0c4,
  0x33c3b3fe,0x315fb2dd,0x28b2aed7,0xaed728b2,0xb0c4b15f,0xaed7b01d,0xabc6ad64,0xa248a8b2,0xabc6b15f,0x315f2bc6,0x33ea3388,0x2ed7326d,
  0x28b2b15f,0x338832dd,0xb01d2d64,0xb1edb3ea,0x301db15f,0x224833c3,0xb0c4b388,0x338830c4,0x326db15f,0xb33b301d,0x33c3ad64,0xb3fe28b2,
  0x33c3b15f,0xb1edabc6,0xa8b23388,0x333bb26d,0x33eab15f,0x2d64b2dd,0xb2dd2d64,0xb15f33ea,0x32ddb15f,0x33feb3c3,0x326db388,0x2d64b0c4,
  0x28b22248,0x2d642bc6,0x301d2ed7,0x315f30c4,0xb01da248,0xb3feb2dd,0xb0c4b33b,0x2d64a8b2,0x326d2248,0x2ed733c3,0xb3c3aed7,0xa248b26d,
  0xb3c3a248,0x315fb01d,0xa8b2333b,0xaed7b3ea,0x33ea2248,0xb388abc6,0x32dd2ed7,0xb1edb0c4,0xb2dda248,0x224832dd,0x326db33b,0xb38828b2,
  0x30c42248,0x333bb3c3,0xabc6aed7,0xb3fe326d,0xabc6a248,0xb1ed301d,0xb3ea333b,0xb33b33ea,0xb26d31ed,0xb33b32dd,0xb3c33388,0xb3fe33ea,
  0xb3c331ed,0xb1ed33c3,0x28b22d64,0x333bb0c4,0xb3ea31ed,0x2d64301d,0x32ddb388,0xb15fa8b2,0xb2dd31ed,0x33feabc6,0xb26dad64,0x2d64326d,
  0xb0c431ed,0x2ed7b2dd,0xabc63388,0x2248b3ea,0xabc631ed,0xb15fb3c3,0x33ea2d64,0xaed730c4,0x28b231ed,0xb388b01d,0xb01db388,0x31ed28b2,
  0x301d31ed,0xa2482bc6,0xb0c4ad64,0xb388b26d,0xb3ea33fe,0xb38833c3,0xb2dd333b,0xb1ed326d,0x32ddb3fe,0x2248b01d,0xb26d2ed7,0xb38833ea,
  0xb0c433fe,0x333babc6,0x2bc6b33b,0xb3fe30c4,0x2bc6b3fe,0xb1ed32dd,0x33eaaed7,0xb33ba8b2,0x28b233fe,0xad64b3c3,0x301d333b,0xb15fb26d,
  0xb01db3fe,0x33fe301d,0xb0c42ed7,0xad64b3ea,0x326d33fe,0xaed72bc6,0xb3c3b33b,0x2248b0c4,0xb3c3b3fe,0xb15fb2dd,0xa8b2aed7,0x2ed728b2,
  0x30c4b15f,0x2ed7b01d,0x2bc6ad64,0x2248a8b2,0x2bc6b15f,0xb15f2bc6,0xb3ea3388,0xaed7326d,0xa8b2b15f,0xb38832dd,0x301d2d64,0x31edb3ea,
  0xb01db15f,0xa24833c3,0x30c4b388,0xb38830c4,0xb26db15f,0x333b301d,0xb3c3ad64,0x33fe28b2,0xb3c3b15f,0x31edabc6,0x28b23388,0xb33bb26d,
  0xb3eab15f,0xad64b2dd,0x32dd2d64,0x315f33ea,0xb2ddb15f,0xb3feb3c3,0xb26db388,0xad64b0c4,0xa8b22248,0xad642bc6,0xb01d2ed7,0xb15f30c4,
  0x301da248,0x33feb2dd,0x30c4b33b,0xad64a8b2,0xb26d2248,0xaed733c3,0x33c3aed7,0x2248b26d,0x33c3a248,0xb15fb01d,0x28b2333b,0x2ed7b3ea,
  0xb3ea2248,0x3388abc6,0xb2dd2ed7,0x31edb0c4,0x32dda248,0xa24832dd,0xb26db33b,0x338828b2,0xb0c42248,0xb33bb3c3,0x2bc6aed7,0x33fe326d,
  0x2bc6a248,0x31ed301d,0x33ea333b,0x333b33ea,0x30c4315f,0x2ed7301d,0x2bc62d64,0x224828b2,0x2bc6315f,0xb15fabc6,0xb3eab388,0xaed7b26d,
  0xa8b2315f,0xb388b2dd,0x301dad64,0x31ed33ea,0xb01d315f,0xa248b3c3,0x30c43388,0xb388b0c4,0xb26d315f,0x333bb01d,0xb3c32d64,0x33fea8b2,
  0xb3c3315f,0x31ed2bc6,0x28b2b388,0xb33b326d,0xb3ea315f,0xad6432dd,0x32ddad64,0x315fb3ea,0xb2dd315f,0xb3fe33c3,0xb26d3388,0xad6430c4,
  0xa8b2a248,0xad64abc6,0xb01daed7,0xb15fb0c4,0x301d2248,0x33fe32dd,0x30c4333b,0xad6428b2,0xb26da248,0xaed7b3c3,0x33c32ed7,0x2248326d,
  0x33c32248,0xb15f301d,0x28b2b33b,0x2ed733ea,0xb3eaa248,0x33882bc6,0xb2ddaed7,0x31ed30c4,0x32dd2248,0xa248b2dd,0xb26d333b,0x3388a8b2,
  0xb0c4a248,0xb33b33c3,0x2bc62ed7,0x33feb26d,0x2bc62248,0x31edb01d,0x33eab33b,0x333bb3ea,0x326d31ed,0x333b32dd,0x33c33388,0x33fe33ea,
  0x33c331ed,0x31ed33c3,0xa8b22d64,0xb33bb0c4,0x33ea31ed,0xad64301d,0xb2ddb388,0x315fa8b2,0x32dd31ed,0xb3feabc6,0x326dad64,0xad64326d,
  0x30c431ed,0xaed7b2dd,0x2bc63388,0xa248b3ea,0x2bc631ed,0x315fb3c3,0xb3ea2d64,0x2ed730c4,0xa8b231ed,0x3388b01d,0x301db388,0xb1ed28b2,
  0xb01d31ed,0x22482bc6,0x30c4ad64,0x3388b26d,0x33ea33fe,0x338833c3,0x32dd333b,0x31ed326d,0xb2ddb3fe,0xa248b01d,0x326d2ed7,0x338833ea,
  0x30c433fe,0xb33babc6,0xabc6b33b,0x33fe30c4,0xabc6b3fe,0x31ed32dd,0xb3eaaed7,0x333ba8b2,0xa8b233fe,0x2d64b3c3,0xb01d333b,0x315fb26d,
  0x301db3fe,0xb3fe301d,0x30c42ed7,0x2d64b3ea,0xb26d33fe,0x2ed72bc6,0x33c3b33b,0xa248b0c4,0x33c3b3fe,0x315fb2dd,0x28b2aed7,0xaed728b2,
  0xb0c4315f,0xaed7301d,0xabc62d64,0xa24828b2,0xabc6315f,0x315fabc6,0x33eab388,0x2ed7b26d,0x28b2315f,0x3388b2dd,0xb01dad64,0xb1ed33ea,
  0x301d315f,0x2248b3c3,0xb0c43388,0x3388b0c4,0x326d315f,0xb33bb01d,0x33c32d64,0xb3fea8b2,0x33c3315f,0xb1ed2bc6,0xa8b2b388,0x333b326d,
  0x33ea315f,0x2d6432dd,0xb2ddad64,0xb15fb3ea,0x32dd315f,0x33fe33c3,0x326d3388,0x2d6430c4,0x28b2a248,0x2d64abc6,0x301daed7,0x315fb0c4,
  0xb01d2248,0xb3fe32dd,0xb0c4333b,0x2d6428b2,0x326da248,0x2ed7b3c3,0xb3c32ed7,0xa248326d,0xb3c32248,0x315f301d,0xa8b2b33b,0xaed733ea,
  0x33eaa248,0xb3882bc6,0x32ddaed7,0xb1ed30c4,0xb2dd2248,0x2248b2dd,0x326d333b,0xb388a8b2,0x30c4a248,0x333b33c3,0xabc62ed7,0xb3feb26d,
  0xabc62248,0xb1edb01d,0xb3eab33b,0xb33bb3ea,0xb26d31ed,0xb33b32dd,0xb3c33388,0xb3fe33ea,0xb3c331ed,0xb1ed33c3,0x28b22d64,0x333bb0c4,
  0xb3ea31ed,0x2d64301d,0x32ddb388,0xb15fa8b2,0xb2dd31ed,0x33feabc6,0xb26dad64,0x2d64326d,0xb0c431ed,0x2ed7b2dd,0xabc63388,0x2248b3ea,
  0xabc631ed,0xb15fb3c3,0x33ea2d64,0xaed730c4,0x28b231ed,0xb388b01d,0xb01db388,0x31ed28b2,0x301d31ed,0xa2482bc6,0xb0c4ad64,0xb388b26d,
  0xb3ea33fe,0xb38833c3,0xb2dd333b,0xb1ed326d,0x32ddb3fe,0x2248b01d,0xb26d2ed7,0xb38833ea,0xb0c433fe,0x333babc6,0x2bc6b33b,0xb3fe30c4,
  0x2bc6b3fe,0xb1ed32dd,0x33eaaed7,0xb33ba8b2,0x28b233fe,0xad64b3c3,0x301d333b,0xb15fb26d,0xb01db3fe,0x33fe301d,0xb0c42ed7,0xad64b3ea,
  0x326d33fe,0xaed72bc6,0xb3c3b33b,0x2248b0c4,0xb3c3b3fe,0xb15fb2dd,0xa8b2aed7,0x2ed728b2,0x29ed29ed,0x29ed29ed,0x29ed29ed,0x29ed29ed,
  0x2bc32a6d,0x2add2bea,0x23c628c4,0xa81da0b2,0x2bc32add,0xa3c6281d,0xabc3aadd,0x23c6a81d,0x29ed2b3b,0xabfea564,0x295fa6d7,0x1a482b88,
  0x25642b88,0xa564ab88,0x25642b88,0xa564ab88,0xa0b22bc3,0x2a6daadd,0xabea23c6,0x28c4281d,0xa8c42bea,0x2a6da0b2,0x28c4abea,0xaa6d20b2,
  0xab3b2bfe,0xa564295f,0x26d79a48,0x2b88a9ed,0x29ed29ed,0x29ed29ed,0x29ed29ed,0x29ed29ed,0xabc3aa6d,0xaaddabea,0xa3c6a8c4,0x281d20b2,
  0x2bc32add,0xa3c6281d,0xabc3aadd,0x23c6a81d,0xa9edab3b,0x2bfe2564,0xa95f26d7,0x9a48ab88,0x25642b88,0xa564ab88,0x25642b88,0xa564ab88,
  0x20b2abc3,0xaa6d2add,0x2beaa3c6,0xa8c4a81d,0xa8c42bea,0x2a6da0b2,0x28c4abea,0xaa6d20b2,0x2b3babfe,0x2564a95f,0xa6d71a48,0xab8829ed,
  0x295f295f,0x295f295f,0x295f295f,0x295f295f,0x23c628c4,0xa81da0b2,0xabc3aa6d,0xaaddabea,0xa3c6281d,0xabc3aadd,0x23c6a81d,0x2bc32add,
  0xa95f26d7,0x9a48ab88,0x29ed2b3b,0xabfea564,0xab882564,0x2b88a564,0xab882564,0x2b88a564,0xabea23c6,0x28c4281d,0x20b2abc3,0xaa6d2add,
  0xaa6d20b2,0xa8c42bea,0x2a6da0b2,0x28c4abea,0xa6d71a48,0xab8829ed,0xab3b2bfe,0xa564295f,0x295f295f,0x295f295f,0x295f295f,0x295f295f,
  0xa3c6a8c4,0x281d20b2,0x2bc32a6d,0x2add2bea,0xa3c6281d,0xabc3aadd,0x23c6a81d,0x2bc32add,0x295fa6d7,0x1a482b88,0xa9edab3b,0x2bfe2564,
  0xab882564,0x2b88a564,0xab882564,0x2b88a564,0x2beaa3c6,0xa8c4a81d,0xa0b22bc3,0x2a6daadd,0xaa6d20b2,0xa8c42bea,0x2a6da0b2,0x28c4abea,
  0x26d79a48,0x2b88a9ed,0x2b3babfe,0x2564a95f,0xabfe2bfe,0xabfe2bfe,0xabfe2bfe,0xabfe2bfe,0xaadd2bea,0xa3c628c4,0x281da0b2,0x2bc3aa6d,
  0xa81d2bc3,0x2adda3c6,0x281dabc3,0xaadd23c6,0x9a482b88,0x29edab3b,0xabfe2564,0x295f26d7,0x26d72b3b,0xa6d7ab3b,0x26d72b3b,0xa6d7ab3b,
  0x2a6d2add,0xabeaa3c6,0x28c4a81d,0x20b22bc3,0x2bea2a6d,0xa0b228c4,0xabeaaa6d,0x20b2a8c4,0x2b8829ed,0x2b3b2bfe,0x2564295f,0xa6d79a48,
  0xabfe2bfe,0xabfe2bfe,0xabfe2bfe,0xabfe2bfe,0x2addabea,0x23c6a8c4,0xa81d20b2,0xabc32a6d,0xa81d2bc3,0x2adda3c6,0x281dabc3,0xaadd23c6,
  0x1a48ab88,0xa9ed2b3b,0x2bfea564,0xa95fa6d7,0x26d72b3b,0xa6d7ab3b,0x26d72b3b,0xa6d7ab3b,0xaa6daadd,0x2bea23c6,0xa8c4281d,0xa0b2abc3,
  0x2bea2a6d,0xa0b228c4,0xabeaaa6d,0x20b2a8c4,0xab88a9ed,0xab3babfe,0xa564a95f,0x26d71a48,0x1a489a48,0x1a489a48,0x1a489a48,0x1a489a48,
  0x281da0b2,0x2bc3aa6d,0x2addabea,0x23c6a8c4,0x2adda3c6,0x281dabc3,0xaadd23c6,0xa81d2bc3,0x2bfea564,0xa95fa6d7,0x9a482b88,0x29edab3b,
  0x2b3ba6d7,0xab3b26d7,0x2b3ba6d7,0xab3b26d7,0x28c4a81d,0x20b22bc3,0xaa6daadd,0x2bea23c6,0x20b2a8c4,0x2bea2a6d,0xa0b228c4,0xabeaaa6d,
  0xa564a95f,0x26d71a48,0x2b8829ed,0x2b3b2bfe,0x1a489a48,0x1a489a48,0x1a489a48,0x1a489a48,0xa81d20b2,0xabc32a6d,0xaadd2bea,0xa3c628c4,
  0x2adda3c6,0x281dabc3,0xaadd23c6,0xa81d2bc3,0xabfe2564,0x295f26d7,0x1a48ab88,0xa9ed2b3b,0x2b3ba6d7,0xab3b26d7,0x2b3ba6d7,0xab3b26d7,
  0xa8c4281d,0xa0b2abc3,0x2a6d2add,0xabeaa3c6,0x20b2a8c4,0x2bea2a6d,0xa0b228c4,0xabeaaa6d,0x2564295f,0xa6d79a48,0xab88a9ed,0xab3babfe,
  0xa95fa95f,0xa95fa95f,0xa95fa95f,0xa95fa95f,0xa3c6a8c4,0x281d20b2,0x2bc32a6d,0x2add2bea,0x23c6a81d,0x2bc32add,0xa3c6281d,0xabc3aadd,
  0x295fa6d7,0x1a482b88,0xa9edab3b,0x2bfe2564,0x2b88a564,0xab882564,0x2b88a564,0xab882564,0x2beaa3c6,0xa8c4a81d,0xa0b22bc3,0x2a6daadd,
  0x2a6da0b2,0x28c4abea,0xaa6d20b2,0xa8c42bea,0x26d79a48,0x2b88a9ed,0x2b3babfe,0x2564a95f,0xa95fa95f,0xa95fa95f,0xa95fa95f,0xa95fa95f,
  0x23c628c4,0xa81da0b2,0xabc3aa6d,0xaaddabea,0x23c6a81d,0x2bc32add,0xa3c6281d,0xabc3aadd,0xa95f26d7,0x9a48ab88,0x29ed2b3b,0xabfea564,
  0x2b88a564,0xab882564,0x2b88a564,0xab882564,0xabea23c6,0x28c4281d,0x20b2abc3,0xaa6d2add,0x2a6da0b2,0x28c4abea,0xaa6d20b2,0xa8c42bea,
  0xa6d71a48,0xab8829ed,0xab3b2bfe,0xa564295f,0x29ed29ed,0x29ed29ed,0x29ed29ed,0x29ed29ed,0x2bc32a6d,0x2add2bea,0x23c628c4,0xa81da0b2,
  0x2bc32add,0xa3c6281d,0xabc3aadd,0x23c6a81d,0x29ed2b3b,0xabfea564,0x295fa6d7,0x1a482b88,0x25642b88,0xa564ab88,0x25642b88,0xa564ab88,
  0xa0b22bc3,0x2a6daadd,0xabea23c6,0x28c4281d,0xa8c42bea,0x2a6da0b2,0x28c4abea,0xaa6d20b2,0xab3b2bfe,0xa564295f,0x26d79a48,0x2b88a9ed,
  0x29ed29ed,0x29ed29ed,0x29ed29ed,0x29ed29ed,0xabc3aa6d,0xaaddabea,0xa3c6a8c4,0x281d20b2,0x2bc32add,0xa3c6281d,0xabc3aadd,0x23c6a81d,
  0xa9edab3b,0x2bfe2564,0xa95f26d7,0x9a48ab88,0x25642b88,0xa564ab88,0x25642b88,0xa564ab88,0x20b2abc3,0xaa6d2add,0x2beaa3c6,0xa8c4a81d,
  0xa8c42bea,0x2a6da0b2,0x28c4abea,0xaa6d20b2,0x2b3babfe,0x2564a95f,0xa6d71a48,0xab8829ed,0x9a481a48,0x9a481a48,0x9a481a48,0x9a481a48,
  0xa81d20b2,0xabc32a6d,0xaadd2bea,0xa3c628c4,0xaadd23c6,0xa81d2bc3,0x2adda3c6,0x281dabc3,0xabfe2564,0x295f26d7,0x1a48ab88,0xa9ed2b3b,
  0xab3b26d7,0x2b3ba6d7,0xab3b26d7,0x2b3ba6d7,0xa8c4281d,0xa0b2abc3,0x2a6d2add,0xabeaa3c6,0xa0b228c4,0xabeaaa6d,0x20b2a8c4,0x2bea2a6d,
  0x2564295f,0xa6d79a48,0xab88a9ed,0xab3babfe,0x9a481a48,0x9a481a48,0x9a481a48,0x9a481a48,0x281da0b2,0x2bc3aa6d,0x2addabea,0x23c6a8c4,
  0xaadd23c6,0xa81d2bc3,0x2adda3c6,0x281dabc3,0x2bfea564,0xa95fa6d7,0x9a482b88,0x29edab3b,0xab3b26d7,0x2b3ba6d7,0xab3b26d7,0x2b3ba6d7,
  0x28c4a81d,0x20b22bc3,0xaa6daadd,0x2bea23c6,0xa0b228c4,0xabeaaa6d,0x20b2a8c4,0x2bea2a6d,0xa564a95f,0x26d71a48,0x2b8829ed,0x2b3b2bfe,
  0xabfe2bfe,0xabfe2bfe,0xabfe2bfe,0xabfe2bfe,0xaadd2bea,0xa3c628c4,0x281da0b2,0x2bc3aa6d,0xa81d2bc3,0x2adda3c6,0x281dabc3,0xaadd23c6,
  0x9a482b88,0x29edab3b,0xabfe2564,0x295f26d7,0x26d72b3b,0xa6d7ab3b,0x26d72b3b,0xa6d7ab3b,0x2a6d2add,0xabeaa3c6,0x28c4a81d,0x20b22bc3,
  0x2bea2a6d,0xa0b228c4,0xabeaaa6d,0x20b2a8c4,0x2b8829ed,0x2b3b2bfe,0x2564295f,0xa6d79a48,0xabfe2bfe,0xabfe2bfe,0xabfe2bfe,0xabfe2bfe,
  0x2addabea,0x23c6a8c4,0xa81d20b2,0xabc32a6d,0xa81d2bc3,0x2adda3c6,0x281dabc3,0xaadd23c6,0x1a48ab88,0xa9ed2b3b,0x2bfea564,0xa95fa6d7,
  0x26d72b3b,0xa6d7ab3b,0x26d72b3b,0xa6d7ab3b,0xaa6daadd,0x2bea23c6,0xa8c4281d,0xa0b2abc3,0x2bea2a6d,0xa0b228c4,0xabeaaa6d,0x20b2a8c4,
  0xab88a9ed,0xab3babfe,0xa564a95f,0x26d71a48,0x3bfb3bff,0x3be53bf2,0x3bbf3bd4,0x3b873ba5,0x3bd03bfb,0x3b013b7c,0x399d3a60,0x378538bc,
  0x35173b52,0xbbc9b7c8,0xb074ba9b,0x3bfe391b,0x319e3b27,0xbbf3b979,0x363cb80a,0x3a2d3bc5,0xba093986,0x3a7eb8f8,0xbae5385f,0x3b3db77a,
  0xbabd393c,0x3bb0b699,0xbc00305b,0x3ba730d7,0xbb2a35c8,0xb8353bb2,0x3a64b1e8,0x3962bbf7,0xba90350b,0xba413bff,0x3602340e,0x3bf6bad8,
  0xac6aa5e4,0xb122af59,0xb402b294,0xb56ab4b7,0xb2deac9c,0xb7bdb5a5,0xb9b3b8d6,0xbb10ba73,0xbb96b676,0xb359bafe,0x3bec3884,0x2a163a29,
  0xbbe0b72c,0x2f27b9d6,0x3b5e3ae8,0xb91633a2,0xb941b9c9,0x38ad3a45,0xb80fbab3,0x36d23b13,0xb850ba0d,0x346f3b4a,0x1fdbbbed,0xb4ab3be8,
  0x3721bb76,0xbace3463,0xb8d13bdd,0x39ebadfb,0x3894bb98,0xb8fd281f,0xbb6a3bbd,0x2e2d3825,0x3b3f3b65,0x3ae83b16,0x3a813ab6,0x3a0d3a49,
  0x3263356a,0xad972b43,0xb5dfb359,0xb8eeb7f3,0xa9b139aa,0xbbedba25,0x3340b889,0x3b983afb,0xbaa2aa16,0xb4cfbb8e,0x3c0038ad,0xb44b38e5,
  0xbb853625,0x3bbdb4c3,0xbbe432ad,0x3bfbaf8b,0xbaacb6d2,0x39243954,0xb65fbace,0x2fbd3bb8,0xb9661648,0xba603bf8,0x383a31cf,0x3b27bbb3,
  0x3219b9eb,0xbb1836f4,0xb9903be5,0x37dd3010,0xb6c6b61a,0xb80ab76f,0xb8a8b85a,0xb93cb8f3,0xbbd7bb87,0xbbf8bbfd,0xbb71bbc9,0xba4dbaf1,
  0xbbfeb9a6,0x305bb91f,0x3bcb3a97,0xb50b37d2,0xb87abbfe,0x3ba13546,0x24523a7e,0xbbb5ba54,0xb576bb63,0x340e3ba3,0xb13bbbd3,0x2c9c3bf2,
  0x386abb3d,0xba2139f8,0x3b57b835,0xbbf13432,0x39e7bc00,0xb8d6adc9,0xbacb3bde,0x372c3457,0x3bdab962,0x3764bb35,0xb9c03122,0xbaf73bef,
  0x398b39cd,0x38fd3946,0x386538b2,0x37853815,0xba85b9c9,0xbb92bb1e,0xbbfebbdd,0xbbc2bbf5,0xb66b3682,0xbb01bb94,0x387fb371,0x3a2d3beb,
  0xbac7bb76,0x3a00ad33,0x36bb3bd4,0xbbeab79b,0xbc0026ad,0x3bf32c38,0xbbd6b109,0x3ba733eb,0x3153bbff,0xb70a3b9e,0x396bba9b,0xbade390c,
  0xb5d4b5bc,0xbbb03b2c,0x32013830,0x3bf6ba67,0x3bccbb52,0x2c06b92e,0xbb83385f,0xb8c73bab,0xb9c5b982,0xba41ba04,0xbab0ba7a,0xbb10bae1,
  0xb8a3b986,0xb52fb74e,0xa94db1e8,0x33d32e91,0xbb54bb4f,0x37bdb523,0x3a9e3bc8,0xb916308d,0x3840b5c8,0x394a3bf9,0xbb42b294,0xb0a6bb0a,
  0x251bbbff,0xaf273bfc,0x327cbbe6,0xb4ab3bc0,0x3be325e4,0xbb2fb4e7,0x39e33884,0xb81aba35,0x3b73bb78,0xb46fb715,0xbbdc3ad1,0x2e2d38cc,
  0x33283676,0x3bfcba19,0x3581bab3,0xba6b3493,0x363136dd,0x34cf3581,0x32c6341a,0x2fbd3153,0xbae1bb65,0xb970ba39,0xb715b889,0xb16cb4f3,
  0xb9a12a7a,0xb924bbfe,0x3a933042,0x37dd3bcc,0x308db9aa,0x3b453b07,0xb94632ad,0xb845bbfa,0xbb68b55e,0x3b1836bb,0xbabab805,0x3a4d38a3,
  0x3bc0b625,0xbbfe2ec3,0x3b9431cf,0xba89b742,0x9cb6b95d,0xbbf8396b,0xb1b63a5c,0x3bb5b840,0x38cc9648,0x3b81bbac,0xac38b85a,0xbbce3933,
  0xbb60bb3a,0xbba1bb83,0xbbd2bbbc,0xbbf1bbe3,0x3815361a,0x39df3907,0x3b2c3a97,0x3be23b9c,0xb9afbbfd,0x3a21294d,0x388e3bee,0xbaf7b328,
  0x3beb39a6,0xb6af37a6,0xba04bbd3,0x3ac42d00,0x360ebb89,0xb7643b42,0x3855baeb,0xb8ee3a85,0x33eb3b63,0x28e8bbf5,0xb5233bde,0x389ebb21,
  0x3c00b9f0,0x2d97b9e3,0xbbdf38db,0xb44b3ac7,0xba673c00,0x358d3487,0x3bfcbab6,0x330fba15,0x3b7a3bf1,0x394a3a93,0x33893764,0xb3d39cb6,
  0x3afb3be2,0x35eb3946,0xb4c328e8,0xbaa9b8cc,0x27763af7,0xbb2fbaba,0x3a76ad97,0x30a63b60,0xaf8b3ac4,0xb994bb94,0x3bf8358d,0xb8743815,
  0xbb4c38ee,0x3bfcb1b6,0xbad5b4cf,0x381a39af,0xbbb3389e,0x3b592c38,0xb76fb970,0xb24b3beb,0xb9d2344b,0xbb923bd2,0xb0f03924,0x3a6bb60e,
  0xb8f3330f,0xbc003b2c,0xb91f3b45,0x323233eb,0xb5b1afbd,0xba00b88e,0xbbc6bb18,0xbbc2bc00,0xb7d2b16c,0xbb6fba04,0xbba3bbfe,0xb86fba67,
  0xbbffb7dd,0x370ab855,0x38b73bf8,0xbbeab631,0xbbf2b845,0x39bcb523,0x2dc93b81,0xbaa5bae1,0xb68dba4d,0xac063bdf,0x382abba1,0xbade39a1,
  0xb457ba89,0xb6543bfc,0x3b16b9df,0xbbd8308d,0x397dbbb5,0xb52fb2c6,0xbbe73a21,0xb8c73b68,0x3a49bbce,0x2311b715,0xba2536af,0xbbd93bc0,
  0xb958b785,0xbb81ba9e,0xbbefbbf3,0xba89bb73,0xbbf7bbc2,0xb9b8bb42,0xaf59b70a,0x384a3328,0xbb8bba2d,0x39dfb27c,0x34263bb0,0xbbceb98b,
  0xb4b7bbea,0x3b6c39e3,0xbafe2c06,0x3185ba85,0xaadebba7,0xb6af3bdc,0x3a58ba41,0xbbe2366b,0x3a29bade,0xbc003581,0x3a45352f,0xb2f7bac7,
  0x3b37bbf6,0x28e8b865,0xbaee37bd,0xbac43c00,0x3b13b8c7,0x3b5cbbfe,0x3463b94a,0xb8993153,0xb9f4bb10,0xb58db87f,0x3029af27,0x389e35d4,
  0x2dfbb3d3,0x399936bb,0x3bf23b2f,0x3ac13bcc,0x3552b916,0x39703bd6,0xbbbab46f,0x330fb9c5,0x3ba530a6,0xb5f7396b,0xb7c8bbfc,0x3be138a3,
  0x3bfdb4ab,0xbb45b201,0x38e038fd,0xb16cbb54,0x391b381a,0xa17fbb83,0xb8f83b92,0x3bcfb840,0x36e82e2d,0x3bfebab0,0x37febb01,0xb845251b,
  0xb77a3a6b,0x3648294d,0x3bb2ba00,0x3a8cbbe3,0xb742b93c,0x2311b340,0x37a6340e,0x3aa93966,0x3b963a4d,0x3b7f3c00,0x380f3a21,0xb0be3219,
  0x3933b50b,0x35eb3be4,0xbbf5b8d6,0x3874b6c6,0x39413bb5,0xbbffb65f,0x38d1b764,0x33ba3bd7,0x3b9c2c9c,0xb994b83a,0x34873ae8,0x324bbbfe,
  0xb7213bf1,0x3b47b990,0xbbbf2d97,0x38c1387a,0x2d00372c,0x3b59b8a8,0x3a39bbed,0xb232b576,0xbbfb3af7,0xb9743b71,0x307434cf,0x3adbb86a,
  0x3b213a0d,0x3c003bcb,0x3b073bbd,0x386f39e7,0x351738ee,0xb599a452,0xbae5b924,0xbbe9bbda,0x3a153b98,0xbb6fb13b,0x2ec3ba60,0x3aa53b3f,
  0xba09344b,0xa884bb57,0x3a643b18,0xbbc3b263,0xb4f33bfb,0x39bcbacb,0xbbac380a,0x3bd8a9b1,0xbb2aafbd,0x36a439c0,0x3402bbf8,0xba6f3aa2,
  0xbbfa3b27,0xb6543a81,0x3907b05b,0x3bd9bb85,0x2c6ab7dd,0xb9da35df,0xbbec3ba1,0xb8203aac,0x3bf53b87,0x3b6c3bec,0x392e3a7e,0x32f73721,
  0xb9e7b785,0xbbfcbb5e,0xba81bbb0,0xb43eb894,0x379b3bfe,0xbc00b80f,0x374eb835,0x38993bfb,0xbb3fba2d,0x3b329fdb,0xb3403a41,0xb8eabbd0,
  0xb90c3b3d,0x3b5cb8d1,0xbbf93122,0x3ac13517,0x29b1bba7,0xb94f3b6a,0x3be4b7bd,0xbaf4b19e,0xbbab3962,0xb9993bbf,0x34e73359,0x3be1ba09,
  0x3b85bbf6,0x353ab99d,0xb83a2f27,0xbbf03abd,0x2e91356a,0xb5f7b074,0xba19b8ad,0xbbcfbb2a,0xb966bb10,0xaba7b63c,0x38a8346f,0x3bb73a90,
  0xbb0aaa16,0xa17fbae5,0x3b1e3ace,0xba8c2c6a,0x36c6b916,0x36ff3c00,0xbbcbb8fd,0x3a50b2de,0xba35b6d2,0x36483a64,0x2d33bbe5,0xb84a3b96,
  0x3bfeb4ab,0xb9fcb602,0x313b3b01,0x37e8bbe0,0x3493b9eb,0xb9b83402,0xbb9e3bc9,0xb1853941,0x35762e2d,0x3b90b9b3,0x3acbbbf3,0x2fefb850,
  0x3a543bcf,0x2884374e,0xb9f8b648,0xbbe9bbab,0x398b3bb7,0xb4db3340,0xbbdcb9fc,0xb911bb85,0xb4323a8c,0xb6a4bbf9,0x3b3539b8,0xbbc3ae91,
  0xb66b3a50,0xad65bbe4,0x38653b90,0xbb0db966,0xbbef384a,0x39da34e7,0x2b43bb6c,0xba6f3b0a,0xbc0037e8,0x3759383a,0x387fbbfc,0xbbf636c6,
  0xb7f33185,0xbb7f3a19,0xbb8e3c00,0xb8203a35,0xb5d42fef,0xba1d38a8,0xbbd63b32,0xbba93bfe,0xb8e5b2f7,0xbbffbb1e,0xb954bb5c,0x30beb493,
  0xb9c5b43e,0xbb9fbbcb,0xb201b94f,0x3a313576,0xbbb8b899,0x3b47ad33,0xb6f43999,0xb3babbf5,0xbb54b8ea,0x3bf9313b,0xbab0353a,0x3790b9e7,
  0xb010bac1,0xb9743b9e,0x3bfdb5f7,0xb8c1b79b,0x251bbaf4,0xbb1b3acb,0x3a9e2ba7,0x2e5fbb3f,0x3af1bbe1,0x3599b92e,0xb546a17f,0xbadb390c,
  0x3b73bbf0,0x3929ba81,0x327cb6ff,0xb49f29b1,0xb825baa9,0x353aaec3,0x3b7c3994,0x3af43bfa,0x360eb0be,0x3bf43a64,0x388e3b47,0xb7372c6a,
  0x38bcb874,0x2ba73bac,0xb979bb59,0x3bf03742,0x3c0033ba,0xbb043402,0x3855b974,0xacce3b96,0x3bc5b24b,0xb6ffb907,0xb6993c00,0x3bb7b933,
  0x363138c1,0x3902bbec,0xbbdf3599,0x34ff3941,0x30d73232,0x39fcb7a6,0x3bffbb6f,0x3a50bb9c,0xb9a13adb,0xb47b380f,0x32c62884,0x3937b721,
  0x3ad8386f,0x3b903bf5,0x35a539bc,0xb7e8ad00,0x3b683be9,0x2ef538d1,0xba93b6a4,0xbb24bbfb,0x3a733aa5,0xbbfcb487,0x39d6b654,0xafef3b21,
  0x1cb63bc3,0xb7b2bbbf,0x3aba39da,0xbbfab517,0xb3a23bd8,0x3b32ba39,0xbb4a2311,0x343e3a15,0xbb603a6f,0x3a3d3074,0x31b6bb7f,0xbb9a3a09,
  0xbbe83bd9,0xb94f3b07,0xa81f35eb,0x38eab4f3,0xb9af3820,0xbbae3ae5,0xbbd23bff,0xba113b2a,0x319e389e,0xb929b426,0xbc00bb45,0xb911bb37,
  0xbbffbac1,0xb805bafe,0x382a217f,0x3bfd3b13,0xbabd330f,0x34dbba58,0x36023bfe,0xbb0db9f4,0xb68dbbe1,0x3a5c3a45,0xbbe7b648,0x3b89adfb,
  0xba90b16c,0x2d653aee,0x39b3bb81,0xbbf63552,0x397dbbcf,0xbbbc3463,0x338939b8,0x39f0bba5,0x32deb845,0xb7593029,0xbb5e39df,0xbba93bfd,
  0x3b7aba8c,0x3beebbf2,0x3a76bb6c,0x36ddb91b,0xbbe0ba89,0xba1dbbba,0x1fdbb6af,0x3a3136e8,0xa776b84a,0x3aeb37c8,0x3ad53c00,0xaa7a377a,
  0xb850bbce,0x3b9f38e0,0xbb6a28e8,0x3790b958,0x3b4cb185,0xb8db38f8,0x30f0bb5c,0x355e3bf7,0x3894bbe2,0xbbf937fe,0x399d358d,0x2e5fbb8b,
  0x39d232f7,0x341abbb2,0xbbc63999,0x395d34b7,0x3bd0bac4,0x3b1bbbef,0x363cb970,0xb49faade,0xb5b13899,0x30422f59,0x38b7b5f7,0x3b3aba29,
  0x3219b3d3,0x3b0438b7,0x3b713bfc,0x34ff397d,0x36e83aa9,0xb8b2adc9,0xbbefbb59,0xb5bcba49,0x3bd730a6,0xb902382a,0xa452bb92,0x39373b7a,
  0xb9583874,0x3371bb16,0x34263c00,0xb982bafb,0x387a381a,0x347bbbe7,0xbb573a00,0x3b242776,0xbb8b324b,0x31093a25,0x3a58bb6f,0xbb4f2f8b,
  0xb86a3a6b,0x2ef53389,0x39c0b70a,0x3bfabb4c,0xaadeb232,0xb83034c3,0xbaee39bc,0xbbff3bb3,0x3bda3bc2,0x37b23a76,0xb5df2c06,0xbb9ab9d2,
  0xbb37b86f,0xba7abbf8,0x3029b654,0x3b7838f3,0x32633bea,0xba3dbad5,0x3c00352f,0xba1135b1,0xb9f4baa5,0x3bc8376f,0xbbba2311,0x39cdb7d2,
  0xbaa23ade,0x3baeb0f0,0xb65fb94a,0xb7373bff,0x3552bbd8,0xbbe6391f,0x38e035eb,0x3682bbf2,0xbaac38c7,0xbbf43bc6,0xb9903b2f,0xacce368d,
  0x3bfdbbd9,0x3ad1bba3,0x37feb994,0x26adb457,0x38a33b9a,0xb8dba452,0xbb83bbae,0x2a7ab86a,0x37423b78,0xbab6b426,0xb907bbe6,0x39aa2ade,
  0xb8403a11,0x341abb57,0x294d3bf4,0xb55ebbda,0xb93339cd,0x3889ba58,0xb7a63ad1,0x3625bb37,0xbbe33737,0x304239c0,0x3b42bb04,0xb95db263,
  0xbb9c3682,0xb2ad3aee,0x3bf5b8b2,0x1648b9f4,0xb3282cce,0xb80535df,0xb9e33902,0xbb3a3aa2,0xad0026ad,0xb1cf3029,0xb4873371,0xb61a3552,
  0xba85b4ff,0xba5cbc00,0x3581b47b,0x3bfd3aac,0xbb21b5bc,0xb85abbba,0x3a393109,0x39a63bfd,0xbac7b937,0x3bbc365f,0xbbfeaef5,0x3b89b219,
  0xba15b982,0x3a9738e0,0xbb07b830,0x3b6336e8,0x3153bb24,0xbbee3990,0x36bb37b2,0x39f0bbd7,0x34f3bb4f,0xbbd337fe,0xaec33a7a,0x3c00b958,
  0x3bccbbfa,0x3aebbb71,0x396bba3d,0x36ddb87a,0x3bfabbff,0x3bdebbef,0x3bacbbc8,0x3b65bb8b,0x3bc03911,0x38303b6a,0xb946ad65,0xbb4fbbd0,
  0x3a353bfd,0xb85f30f0,0xbb1ebbbc,0x35c8b5b1,0x38cc3b0d,0xba7ab99d,0x3b943759,0xbbffb19e,0xb4933b89,0x31e8bbc6,0xad333bee,0xa5e4bbff,
  0xb8153bf6,0x3bc8b63c,0xac38ba1d,0xbb783abd,0xbbf539f0,0x329438b7,0x3b9ebaeb,0xb676b68d,0xbbeb3ba9,0xbbe63c00,0xbb2c3b9f,0xb9cd3a90,
  0xb79b36dd,0xb884382a,0xb92e38db,0xb9c9397d,0x33eb3a31,0xbad1b602,0xba04bbf9,0x3682b2de,0xb90c2a7a,0xbab3bbe7,0x374eb41a,0x3b763b7a,
  0xba673790,0x38b2b9b3,0xb5233b1b,0x26adbbe0,0xbbabb55e,0x3bdd3389,0xbbf9b042,0x3bff2776,0xbae12e5f,0xb3713b5e,0x3bfcb929,0xb5bcb850,
  0xae91b95d,0xbbd43a76,0x34e73805,0x3b52bb4c,0x308db49f,0xb1091fdb,0xb71534db,0xb9823894,0x3b0abb3a,0x3a9bbad5,0x3a19ba5c,0x3986b9d2,
  0x2f8bb7e8,0x3bde3979,0x376f3b32,0xb9aab0d7,0x3bb83b24,0xb1223855,0xbbfdba3d,0xaa16b9a1,0x3bb3afef,0xbab63699,0x391fb94f,0xb6253ad8,
  0x30103bfa,0xb359bbdf,0x35463bae,0xb6d2bb68,0x38f3343e,0x3889bbff,0xbba3353a,0x96483a73,0xbaf13b9a,0x38ad32c6,0x39f8bbf4,0xb9eb9cb6,
  0xb7d238ea,0xb2ad35a5,0x2dc92ba7,0x361ab3a2,0xba543a11,0xbace3a93,0xbb353b04,0xbb873b60,0x3bf23af4,0x31cf39d6,0xbb16b6ff,0xb9a6bbe8,
  0xb4323737,0xbbe5baba,0x2b43b902,0x3bfe39af,0x34573bf0,0xb85abb4a,0x3a2539fc,0xbb63b825,0xbbef2cce,0x3bc9b1b6,0xbb8e347b,0x3b3db60e,
  0xba493bb7,0x3a97a81f,0x34c3bb90,0xbc0038bc,0xb7f3b4ff,0xba7e3bd2,0x39542ef5,0x3962bc00,0xbafb3a50,0xbbd33b7c,0xbbf83bfc,0xbb653bc5,
  0x38e5b937,0x3835b88e,0x36f4b7b2,0x356ab631,0xbb13bbe9,0x31e8b6f4,0x3bf239da,0x36763af1,0x3be83911,0x340e3ab0,0xbb7cb759,0xb72cbb73,
  0x2dfbbbc3,0x32943bfd,0xb7c8bb7f,0x39c93a54,0x38253b0d,0xb8d6ba9e,0x39793a1d,0xba0db98b,0x3ba5ba6f,0xb884b546,0xb8f83bff,0x3b76b432,
  0xb8bc3bf6,0x3ae8b27c,0x3699bb9f,0xbb98366b,0x391bb820,0x3ab3b9f8,0x3bb2bb47,0x3bffbbef,0xbbc53ba9,0xbbed3bdc,0xbbff3bf9,0xbbfb3c00,
  0x377ab0be,0x3bdd3b35,0x2f593974,0xbb52b7f3,0x30d73a31,0xbbbdb865,0xb5a5bb1b,0x3b2735d4,0x3bf733ba,0xbbd42b43,0x3afeb599,0xb98638e5,
  0xbad83790,0x3a60b87f,0xb9d63929,0x393cb9c5,0x34b738c1,0x3a9bbb8e,0xba45a884,0xb5c83bb8,0xba732e5f,0xb80a3bd6,0x3b4ab4db,0x350bbb54,
  0xba293adb,0xb85f3954,0xb46336a4,0x25e43010,0x33a2b49f,0x305bb201,0x281fad65,0xac9c251b,0x3f803f80,0x3f803f80,0x3f803f80,0x3f803f80,
  0x3f803f80,0x3f803f80,0x3f803f80,0x3f803f80,0x3f803f80,0x3f803f80,0x3f803f80,0x3f803f80,0x3f803f80,0x3f803f80,0x3f803f80,0x3f803f80,
  0x3f803f80,0x3f803f80,0x3f803f80,0x3f803f80,0x3f803f80,0x3f803f80,0x3f803f80,0x3f803f80,0x3f803f80,0x3f803f80,0x3f803f80,0x3f803f80,
  0x3f803f80,0x3f803f80,0x3f803f80,0x3f803f80,0x3f803f80,0x3f803f80,0x3f803f80,0x3f803f80,0x3f803f80,0x3f803f80,0x3f803f80,0x3f803f80,
  0x3f803f80,0x3f803f80,0x3f803f80,0x3f803f80,0x3f803f80,0x3f803f80,0x3f803f80,0x3f803f80,0x3f803f80,0x3f803f80,0x3f803f80,0x3f803f80,
  0x3f803f80,0x3f803f80,0x3f803f80,0x3f803f80,0x3f803f80,0x3f803f80,0x3f803f80,0x3f803f80,0x3f803f80,0x3f803f80,0x3f803f80,0x3f803f80,
  0x3f803f80,0x3f803f80,0x3f803f80,0x3f803f80,0x3f803f80,0x3f803f80,0x3f803f80,0x3f803f80,0x3f803f80,0x3f803f80,0x3f803f80,0x3f803f80,
  0x3f803f80,0x3f803f80,0x3f803f80,0x3f803f80,0x3f803f80,0x3f803f80,0x3f803f80,0x3f803f80,0x3f803f80,0x3f803f80,0x3f803f80,0x3f803f80,
  0x3f803f80,0x3f803f80,0x3f803f80,0x3f803f80,0x3f803f80,0x3f803f80,0x3f803f80,0x3f803f80,0x3f803f80,0x3f803f80,0x3f803f80,0x3f803f80,
  0x3f803f80,0x3f803f80,0x3f803f80,0x3f803f80,0x3f803f80,0x3f803f80,0x3f803f80,0x3f803f80,0x3f803f80,0x3f803f80,0x3f803f80,0x3f803f80,
  0x3f803f80,0x3f803f80,0x3f803f80,0x3f803f80,0x3f803f80,0x3f803f80,0x3f803f80,0x3f803f80,0x3f803f80,0x3f803f80,0x3f803f80,0x3f803f80,
  0x3f803f80,0x3f803f80,0x3f803f80,0x3f803f80,0x3f803f80,0x3f803f80,0x3f803f80,0x3f803f80,0x3f803f80,0x3f803f80,0x3f803f80,0x3f803f80,
  0x3f803f80,0x3f803f80,0x3f803f80,0x3f803f80,0x3f803f80,0x3f803f80,0x3f803f80,0x3f803f80,0x3f803f80,0x3f803f80,0x3f803f80,0x3f803f80,
  0x3f803f80,0x3f803f80,0x3f803f80,0x3f803f80,0x3f803f80,0x3f803f80,0x3f803f80,0x3f803f80,0x3f803f80,0x3f803f80,0x3f803f80,0x3f803f80,
  0x3f803f80,0x3f803f80,0x3f803f80,0x3f803f80,0x3f803f80,0x3f803f80,0x3f803f80,0x3f803f80,0x3f803f80,0x3f803f80,0x3f803f80,0x3f803f80,
  0x3f803f80,0x3f803f80,0x3f803f80,0x3f803f80,0x3f803f80,0x3f803f80,0x3f803f80,0x3f803f80,0x3f803f80,0x3f803f80,0x3f803f80,0x3f803f80,
  0x3f803f80,0x3f803f80,0x3f803f80,0x3f803f80,0x3f803f80,0x3f803f80,0x3f803f80,0x3f803f80,0x3f803f80,0x3f803f80,0x3f803f80,0x3f803f80,
  0x3f803f80,0x3f803f80,0x3f803f80,0x3f803f80,0x3f803f80,0x3f803f80,0x3f803f80,0x3f803f80,0x3f803f80,0x3f803f80,0x3f803f80,0x3f803f80,
  0x3f803f80,0x3f803f80,0x3f803f80,0x3f803f80,0x3f803f80,0x3f803f80,0x3f803f80,0x3f803f80,0x3f803f80,0x3f803f80,0x3f803f80,0x3f803f80,
  0x3f803f80,0x3f803f80,0x3f803f80,0x3f803f80,0x3f803f80,0x3f803f80,0x3f803f80,0x3f803f80,0x3f803f80,0x3f803f80,0x3f803f80,0x3f803f80,
  0x3f803f80,0x3f803f80,0x3f803f80,0x3f803f80,0x3f803f80,0x3f803f80,0x3f803f80,0x3f803f80,0x3f803f80,0x3f803f80,0x3f803f80,0x3f803f80,
  0x3f803f80,0x3f803f80,0x3f803f80,0x3f803f80,0x3f803f80,0x3f803f80,0x3f803f80,0x3f803f80,0x3f803f80,0x3f803f80,0x3f803f80,0x3f803f80,
  0x3f803f80,0x3f803f80,0x3f803f80,0x3f803f80,0x3f803f80,0x3f803f80,0x3f803f80,0x3f803f80,0x3f803f80,0x3f803f80,0x3f803f80,0x3f803f80,
  0x3f803f80,0x3f803f80,0x3f803f80,0x3f803f80,0x3f803f80,0x3f803f80,0x3f803f80,0x3f803f80,0x3f803f80,0x3f803f80,0x3f803f80,0x3f803f80,
  0x3f803f80,0x3f803f80,0x3f803f80,0x3f803f80,0x3f803f80,0x3f803f80,0x3f803f80,0x3f803f80,0x3f803f80,0x3f803f80,0x3f803f80,0x3f803f80,
  0x3f803f80,0x3f803f80,0x3f803f80,0x3f803f80,0x3f803f80,0x3f803f80,0x3f803f80,0x3f803f80,0x3f803f80,0x3f803f80,0x3f803f80,0x3f803f80,
  0x3f803f80,0x3f803f80,0x3f803f80,0x3f803f80,0x3f803f80,0x3f803f80,0x3f803f80,0x3f803f80,0x3f803f80,0x3f803f80,0x3f803f80,0x3f803f80,
  0x3f803f80,0x3f803f80,0x3f803f80,0x3f803f80,0x3f803f80,0x3f803f80,0x3f803f80,0x3f803f80,0x3f803f80,0x3f803f80,0x3f803f80,0x3f803f80,
  0x3f803f80,0x3f803f80,0x3f803f80,0x3f803f80,0x3f803f80,0x3f803f80,0x3f803f80,0x3f803f80,0x3f803f80,0x3f803f80,0x3f803f80,0x3f803f80,
  0x3f803f80,0x3f803f80,0x3f803f80,0x3f803f80,0x3f803f80,0x3f803f80,0x3f803f80,0x3f803f80,0x3f803f80,0x3f803f80,0x3f803f80,0x3f803f80,
  0x3f803f80,0x3f803f80,0x3f803f80,0x3f803f80,0x3f803f80,0x3f803f80,0x3f803f80,0x3f803f80,0x3f803f80,0x3f803f80,0x3f803f80,0x3f803f80,
  0x3f803f80,0x3f803f80,0x3f803f80,0x3f803f80,0x3f803f80,0x3f803f80,0x3f803f80,0x3f803f80,0x3f803f80,0x3f803f80,0x3f803f80,0x3f803f80,
  0x3f803f80,0x3f803f80,0x3f803f80,0x3f803f80,0x3f803f80,0x3f803f80,0x3f803f80,0x3f803f80,0x3f803f80,0x3f803f80,0x3f803f80,0x3f803f80,
  0x3f803f80,0x3f803f80,0x3f803f80,0x3f803f80,0x3f803f80,0x3f803f80,0x3f803f80,0x3f803f80,0x3f803f80,0x3f803f80,0x3f803f80,0x3f803f80,
  0x3f803f80,0x3f803f80,0x3f803f80,0x3f803f80,0x3f803f80,0x3f803f80,0x3f803f80,0x3f803f80,0x3f803f80,0x3f803f80,0x3f803f80,0x3f803f80,
  0x3f803f80,0x3f803f80,0x3f803f80,0x3f803f80,0x3f803f80,0x3f803f80,0x3f803f80,0x3f803f80,0x3f803f80,0x3f803f80,0x3f803f80,0x3f803f80,
  0x3f803f80,0x3f803f80,0x3f803f80,0x3f803f80,0x3f803f80,0x3f803f80,0x3f803f80,0x3f803f80,0x3f803f80,0x3f803f80,0x3f803f80,0x3f803f80,
  0x3f803f80,0x3f803f80,0x3f803f80,0x3f803f80,0x3f803f80,0x3f803f80,0x3f803f80,0x3f803f80,0x3f803f80,0x3f803f80,0x3f803f80,0x3f803f80,
  0x3f803f80,0x3f803f80,0x3f803f80,0x3f803f80,0x3f803f80,0x3f803f80,0x3f803f80,0x3f803f80,0x3f803f80,0x3f803f80,0x3f803f80,0x3f803f80,
  0x3f803f80,0x3f803f80,0x3f803f80,0x3f803f80,0x3f803f80,0x3f803f80,0x3f803f80,0x3f803f80,0x3f803f80,0x3f803f80,0x3f803f80,0x3f803f80,
  0x3f803f80,0x3f803f80,0x3f803f80,0x3f803f80,0x3f803f80,0x3f803f80,0x3f803f80,0x3f803f80,0x3f803f80,0x3f803f80,0x3f803f80,0x3f803f80,
  0x3f803f80,0x3f803f80,0x3f803f80,0x3f803f80,0x3f803f80,0x3f803f80,0x3f803f80,0x3f803f80,0x3f803f80,0x3f803f80,0x3f803f80,0x3f803f80,
  0x3f803f80,0x3f803f80,0x3f803f80,0x3f803f80,0x3f803f80,0x3f803f80,0x3f803f80,0x3f803f80,0x3f803f80,0x3f803f80,0x3f803f80,0x3f803f80,
  0x3f803f80,0x3f803f80,0x3f803f80,0x3f803f80,
};

__device__ __align__(128) float    g_part[16][8][2176];
__device__ __align__(128) float    g_kv[16][2176];
constexpr int OBLK = 16 * 1024 + 32;
__device__ __align__(128) uint4    g_o[16 * OBLK];
#define GSTAMP(role, i) do {} while (0)
#define STAMP(role, i) do {} while (0)
#define PDUMP(role) do {} while (0)
#define PROF_SMEM 0

constexpr int STAGE_BYTES = 57344;
constexpr int OFF_H = 4 * 16384, OFF_VP = 9 * 16384, OFF_SPARE = 10 * 16384;
constexpr int OFF_XT = 172032, XT_STRIDE = 4112;
constexpr int OFF_BAR = 204928, OFF_EPOCH = OFF_BAR + 640, OFF_EX = OFF_BAR + 656, OFF_D = OFF_BAR + 672, OFF_SCALE = OFF_BAR + 704;
constexpr int OFF_F2F = 205824, OFF_F2I = 207872, OFF_F4 = 209920, OFF_ONES = 214016, OFF_KVB = 214016;
constexpr int OFF_STG = 219136, STG_STRIDE = 4352, SMEM_TOTAL = 232192 + PROF_SMEM;
enum { B_FULL1 = 0, B_EMPTY1 = 3, B_Q = 6, B_ODONE1 = 7, B_O1RDY = 8, B_H = 9, B_XRAW = 10, B_XT = 11, B_KV = 12, B_Y = 13,  B_AFREE = 15,
       B_STG = 18, B_ODONE = 24, B_XFREE = 25, B_FULL2 = 33, B_CONS2 = 49, B_SFREE = 14, B_KV1 = 61, B_OLOC = 60, B_PKRDY = 62, B_PKFREE = 64, B_H2 = 65, B_G1DONE = 66, B_COUNT = 67, B_FIRST = 67 };
constexpr uint64_t SLOT_A = 0x6859468594685948ull, SLOT_B = 0x7103271032710326ull;
constexpr int NPRE = 6, BEARLY = 3;
__host__ __device__ constexpr int bar_count(int i) {
  return i < B_EMPTY1 ? 1 : i < B_Q ? 4 : i == B_XT ? 4 : i == B_H ? 4 : (i == B_SFREE || i == B_G1DONE) ? 2 : i >= B_PKFREE ? 4 : i >= B_PKRDY ? 8 : i == B_Y ? 9
       : (i >= B_AFREE && i < B_STG) ? 16 : (i == B_ODONE || i == B_ODONE1) ? 8 : (i >= B_XFREE && i < B_FULL2) ? 4
       : i == B_KV1 ? 1 : i == B_OLOC ? 2 : i >= B_CONS2 ? 4 : (i >= B_FULL2 && i < B_FULL2 + NPRE) ? 2 : 1;
}
__host__ __device__ constexpr uint64_t bar_counts(int r) {
  uint64_t v = 0;
  for (int w = 0; w < 11; w++) v |= (uint64_t)(bar_count(1 + 11 * r + w) - 1) << (4 * w);
  return v;
}
constexpr uint32_t SW128 = 64 | (1u << 30);
constexpr int SPIN_LIMIT = 1 << 22;
#define SPLIT0 2
#define OLOC 1
#define G2E 1
#define G2P 1
#define RC 200
#define PFD 3
#define PD1 700
#define PD2 450
#define QPF 6
#define BPACE 250
#define OCH 3
#define O1D 0
#define HOLD2 12
#define D1 100
#define TRICK 3
#define HSTART 1500
#define PACE 800

__device__ __forceinline__ uint32_t smem_u32(const void* p) { return (uint32_t)__cvta_generic_to_shared(p); }
__device__ __forceinline__ void wg_fence() { asm volatile("wgmma.fence.sync.aligned;" ::: "memory"); }
__device__ __forceinline__ void wg_commit() { asm volatile("wgmma.commit_group.sync.aligned;" ::: "memory"); }
template <int N> __device__ __forceinline__ void wg_wait() { asm volatile("wgmma.wait_group.sync.aligned %0;" ::"n"(N) : "memory"); }
template <int N> __device__ __forceinline__ void keep(float (&d)[N]) {
#pragma unroll
  for (int i = 0; i < N; i++) asm volatile("" : "+f"(d[i])::"memory");
}
__device__ __forceinline__ void mbar_init(uint32_t bar, int cnt) { asm volatile("mbarrier.init.shared::cta.b64 [%0], %1;" ::"r"(bar), "r"(cnt)); }
__device__ __forceinline__ void mbar_expect(uint32_t bar, int bytes) { asm volatile("mbarrier.arrive.expect_tx.shared::cta.b64 _, [%0], %1;" ::"r"(bar), "r"(bytes) : "memory"); }
__device__ __forceinline__ void mbar_arrive(uint32_t bar) { asm volatile("mbarrier.arrive.shared::cta.b64 _, [%0];" ::"r"(bar) : "memory"); }
__device__ __forceinline__ void mbar_arrive_cl(uint32_t bar, uint32_t cta) {
  asm volatile("{\n.reg .b32 r;\nmapa.shared::cluster.u32 r, %0, %1;\nmbarrier.arrive.shared::cluster.b64 _, [r];\n}\n" ::"r"(bar), "r"(cta) : "memory");
}
__device__ __forceinline__ void mbar_wait(uint32_t bar, uint32_t parity) {
  asm volatile("{\n.reg .pred p;\n.reg .u32 n;\nmov.u32 n, 0;\n"
               "W_%=:\nmbarrier.try_wait.parity.shared::cta.b64 p, [%0], %1;\n@p bra D_%=;\n"
               "add.u32 n, n, 1;\nsetp.lt.u32 p, n, %2;\n@p bra W_%=;\ntrap;\nD_%=:\n}\n" ::"r"(bar), "r"(parity), "n"(SPIN_LIMIT) : "memory");
}
__device__ __forceinline__ void fence_async() { asm volatile("fence.proxy.async.shared::cta;" ::: "memory"); }
__device__ __forceinline__ void bar_sync(int id) { asm volatile("bar.sync %0, 128;" ::"r"(id) : "memory"); }
__device__ __forceinline__ void tma2d(uint32_t dst, const CUtensorMap* m, int c0, int c1, uint32_t bar) {
  asm volatile("cp.async.bulk.tensor.2d.shared::cluster.global.mbarrier::complete_tx::bytes [%0], [%1, {%3, %4}], [%2];"
               ::"r"(dst), "l"(m), "r"(bar), "r"(c0), "r"(c1) : "memory");
}
__device__ __forceinline__ void tma2d_mc(uint32_t dst, const CUtensorMap* m, int c0, int c1, uint32_t bar) {
  asm volatile("cp.async.bulk.tensor.2d.shared::cluster.global.mbarrier::complete_tx::bytes.multicast::cluster [%0], [%1, {%3, %4}], [%2], %5;"
               ::"r"(dst), "l"(m), "r"(bar), "r"(c0), "r"(c1), "h"((uint16_t)3) : "memory");
}
__device__ __forceinline__ void tma3d(uint32_t dst, const CUtensorMap* m, int c0, int c1, int c2, uint32_t bar) {
  asm volatile("cp.async.bulk.tensor.3d.shared::cluster.global.mbarrier::complete_tx::bytes [%0], [%1, {%3, %4, %5}], [%2];"
               ::"r"(dst), "l"(m), "r"(bar), "r"(c0), "r"(c1), "r"(c2) : "memory");
}
__device__ __forceinline__ void tma4d(uint32_t dst, const CUtensorMap* m, int c0, int c1, int c2, int c3, uint32_t bar) {
  asm volatile("cp.async.bulk.tensor.4d.shared::cluster.global.mbarrier::complete_tx::bytes [%0], [%1, {%3, %4, %5, %6}], [%2];"
               ::"r"(dst), "l"(m), "r"(bar), "r"(c0), "r"(c1), "r"(c2), "r"(c3) : "memory");
}
__device__ __forceinline__ void bulk_ld(uint32_t dst, const void* src, int bytes, uint32_t bar) {
  asm volatile("cp.async.bulk.shared::cluster.global.mbarrier::complete_tx::bytes [%0], [%1], %2, [%3];" ::"r"(dst), "l"(src), "r"(bytes), "r"(bar) : "memory");
}
__device__ __forceinline__ void bulk_ld_mc(uint32_t dst, const void* src, int bytes, uint32_t bar) {
  asm volatile("cp.async.bulk.shared::cluster.global.mbarrier::complete_tx::bytes.multicast::cluster [%0], [%1], %2, [%3], %4;"
               ::"r"(dst), "l"(src), "r"(bytes), "r"(bar), "h"((uint16_t)3) : "memory");
}
__device__ __forceinline__ void tma2d_st(const CUtensorMap* m, uint32_t src, int c0, int c1) {
  asm volatile("cp.async.bulk.tensor.2d.global.shared::cta.bulk_group [%0, {%2, %3}], [%1];" ::"l"(m), "r"(src), "r"(c0), "r"(c1) : "memory");
}
__device__ __forceinline__ void ldsm4(uint32_t (&r)[4], uint32_t a) {
  asm volatile("ldmatrix.sync.aligned.m8n8.x4.shared.b16 {%0,%1,%2,%3}, [%4];" : "=r"(r[0]), "=r"(r[1]), "=r"(r[2]), "=r"(r[3]) : "r"(a) : "memory");
}
__device__ __forceinline__ void ldsm4t(uint32_t (&r)[4], uint32_t a) {
  asm volatile("ldmatrix.sync.aligned.m8n8.x4.trans.shared.b16 {%0,%1,%2,%3}, [%4];" : "=r"(r[0]), "=r"(r[1]), "=r"(r[2]), "=r"(r[3]) : "r"(a) : "memory");
}
__device__ __forceinline__ void stsm4(uint32_t a, uint32_t r0, uint32_t r1, uint32_t r2, uint32_t r3) {
  asm volatile("stmatrix.sync.aligned.m8n8.x4.shared.b16 [%0], {%1,%2,%3,%4};" ::"r"(a), "r"(r0), "r"(r1), "r"(r2), "r"(r3) : "memory");
}
__device__ __forceinline__ uint32_t pk2(float lo, float hi) { uint32_t r; asm("cvt.rn.bf16x2.f32 %0, %1, %2;" : "=r"(r) : "f"(hi), "f"(lo)); return r; }
__device__ __forceinline__ uint32_t hmul(uint32_t a, uint32_t b) { uint32_t r; asm("mul.rn.bf16x2 %0, %1, %2;" : "=r"(r) : "r"(a), "r"(b)); return r; }
__device__ __forceinline__ uint32_t hadd(uint32_t a, uint32_t b) { uint32_t r; asm("add.rn.bf16x2 %0, %1, %2;" : "=r"(r) : "r"(a), "r"(b)); return r; }
__device__ __forceinline__ uint32_t hmin(uint32_t a, uint32_t b) { uint32_t r; asm("min.bf16x2 %0, %1, %2;" : "=r"(r) : "r"(a), "r"(b)); return r; }
__device__ __forceinline__ uint32_t hmaxabs(uint32_t a, uint32_t b) { uint32_t r; asm("max.xorsign.abs.bf16x2 %0, %1, %2;" : "=r"(r) : "r"(a), "r"(b)); return r; }
__device__ __forceinline__ float ex2(float x) { float r; asm("ex2.approx.ftz.f32 %0, %1;" : "=f"(r) : "f"(x)); return r; }
__device__ __forceinline__ float rcp_fast(float x) { float r; asm("rcp.approx.ftz.f32 %0, %1;" : "=f"(r) : "f"(x)); return r; }
__device__ __forceinline__ uint32_t phi2(float lo, float hi) {
  uint32_t t;
  asm("cvt.rn.relu.bf16x2.f32 %0, %1, %2;" : "=r"(t) : "f"(hi), "f"(lo));
  const uint32_t e = pk2(ex2(lo * 1.4426950408889634f), ex2(hi * 1.4426950408889634f));
  return hadd(hadd(t, hmin(e, 0x3F803F80u)), 0x35863586u);
}
__device__ __forceinline__ bool opaque_true() { uint32_t v; asm volatile("mov.u32 %0, %%nctaid.y;" : "=r"(v)); return v != 0; }
__device__ __forceinline__ int norm_exp(uint32_t (&v)[32], float f0) {
  uint32_t m[4] = {hmaxabs(__float_as_uint(f0) >> 16, v[0]), v[1], v[2], v[3]};
#pragma unroll
  for (int i = 4; i < 32; i++) m[i & 3] = hmaxabs(m[i & 3], v[i]);
  m[0] = hmaxabs(hmaxabs(m[0], m[1]), hmaxabs(m[2], m[3]));
  const int e = min(max((int)(__reduce_max_sync(~0u, max(m[0] & 0x7FFFu, (m[0] >> 16) & 0x7FFFu)) >> 7), 1), 253);
  if (e > 141) {
#pragma unroll
    for (int i = 0; i < 32; i++) v[i] = hmul(v[i], 0x07000700u);
  }
  return e;
}
__device__ __forceinline__ void norm_cvt(uint32_t (&v)[32], float f0, int e) {
  const uint32_t sc = (e > 141 ? 255 - e : 142 - e) * 0x00800080u;
#pragma unroll
  for (int i = 0; i < 32; i++) {
    const uint32_t a = hmul(v[i], sc);
    v[i] = (a & 0x0FFF0FFFu) * 7 + a;
  }
  v[0] = __byte_perm(v[0], __half_as_ushort(__float2half_rn(f0 * __uint_as_float((254 - e) << 23))), 0x3254);
}
__device__ __forceinline__ void poll_ge(const unsigned* p, unsigned target) {
#pragma unroll 1
  for (int n = 0; n < SPIN_LIMIT; n++) {
    unsigned v;
    asm volatile("ld.relaxed.gpu.global.u32 %0, [%1];" : "=r"(v) : "l"(p) : "memory");
    if (__all_sync(~0u, (int)(v - target) >= 0)) { asm volatile("fence.acquire.gpu;" ::: "memory"); return; }
  }
  __trap();
}

__device__ __forceinline__ bool elect_one() {
  uint32_t p;
  asm volatile("{\n.reg .pred p;\nelect.sync _|p, 0xffffffff;\nselp.u32 %0, 1, 0, p;\n}\n" : "=r"(p));
  return p;
}
__device__ __forceinline__ uint4 ld_na4(const void* p) {
  uint4 v;
  asm volatile("ld.global.L1::no_allocate.v4.u32 {%0,%1,%2,%3}, [%4];" : "=r"(v.x), "=r"(v.y), "=r"(v.z), "=r"(v.w) : "l"(p) : "memory");
  return v;
}
__device__ __forceinline__ void st_cg4(void* p, uint4 v) {
  asm volatile("st.global.cg.v4.u32 [%0], {%1,%2,%3,%4};" ::"l"(p), "r"(v.x), "r"(v.y), "r"(v.z), "r"(v.w) : "memory");
}
__device__ __forceinline__ uint32_t mapa(uint32_t a, uint32_t cta) { uint32_t r; asm("mapa.shared::cluster.u32 %0, %1, %2;" : "=r"(r) : "r"(a), "r"(cta)); return r; }
__device__ __forceinline__ void st_async(uint32_t a, uint32_t v, uint32_t bar) {
  asm volatile("st.async.weak.shared::cluster.mbarrier::complete_tx::bytes.b32 [%0], %1, [%2];" ::"r"(a), "r"(v), "r"(bar) : "memory");
}
__device__ __forceinline__ void st_async4(uint32_t a, uint32_t x, uint32_t y, uint32_t z, uint32_t w, uint32_t bar) {
  asm volatile("st.async.weak.shared::cluster.mbarrier::complete_tx::bytes.v4.b32 [%0], {%1,%2,%3,%4}, [%5];" ::"r"(a), "r"(x), "r"(y), "r"(z), "r"(w), "r"(bar) : "memory");
}
__device__ __forceinline__ void tma3d_st(const CUtensorMap* m, uint32_t src, int c0, int c1, int c2) {
  asm volatile("cp.async.bulk.tensor.3d.global.shared::cta.bulk_group [%0, {%2, %3, %4}], [%1];" ::"l"(m), "r"(src), "r"(c0), "r"(c1), "r"(c2) : "memory");
}
__device__ __forceinline__ uint4 ld_rlx4(const void* p) {
  uint4 v;
  asm volatile("{\n.reg .b128 t;\n.reg .b64 a, b;\nld.relaxed.gpu.global.b128 t, [%4];\nmov.b128 {a, b}, t;\nmov.b64 {%0, %1}, a;\nmov.b64 {%2, %3}, b;\n}\n"
               : "=r"(v.x), "=r"(v.y), "=r"(v.z), "=r"(v.w) : "l"(p) : "memory");
  return v;
}
__device__ __forceinline__ void ld_stale4(uint4& v, const void* p, uint32_t tag) {
  asm volatile("{\n.reg .b128 t;\n.reg .b64 a, b;\n.reg .b32 x;\n.reg .pred p;\n"
               "lop3.b32 x, %0, %5, 1, 0x28;\nsetp.ne.u32 p, x, 0;\n"
               "mov.b64 a, {%0, %1};\nmov.b64 b, {%2, %3};\nmov.b128 t, {a, b};\n"
               "@p ld.relaxed.gpu.global.b128 t, [%4];\n"
               "mov.b128 {a, b}, t;\nmov.b64 {%0, %1}, a;\nmov.b64 {%2, %3}, b;\n}\n"
               : "+r"(v.x), "+r"(v.y), "+r"(v.z), "+r"(v.w) : "l"(p), "r"(tag) : "memory");
}
__device__ __forceinline__ void st_tag4(void* p, float a, float b, float c, float d, uint32_t tag) {
  asm volatile("{\n.reg .b128 t;\n.reg .b64 a, b;\nmov.b64 a, {%1, %2};\nmov.b64 b, {%3, %4};\nmov.b128 t, {a, b};\nst.relaxed.gpu.global.b128 [%0], t;\n}\n"
               ::"l"(p), "r"((__float_as_uint(a) & ~1u) | tag), "f"(b), "f"(c), "f"(d) : "memory");
}
__device__ __forceinline__ uint32_t stale8(const uint4 (&f)[8], uint32_t tag) {
  uint32_t r[4];
#pragma unroll
  for (int i = 0; i < 4; i++) asm("lop3.b32 %0, %1, %2, %3, 0x7E;" : "=r"(r[i]) : "r"(f[2 * i].x), "r"(f[2 * i + 1].x), "r"(tag));
  asm("lop3.b32 %0, %0, %1, %2, 0xFE;" : "+r"(r[0]) : "r"(r[1]), "r"(r[2]));
  return r[0] | r[3];
}

struct ConvC { uint32_t a1[2][4], wa[2], wb[2], sg; };
__device__ __forceinline__ uint64_t dsc(uint32_t lo, uint32_t hi) { return ((uint64_t)hi << 32) | lo; }
__device__ __forceinline__ uint32_t hfma(uint32_t a, uint32_t b, uint32_t c) { uint32_t r; asm("fma.rn.f16x2 %0, %1, %2, %3;" : "=r"(r) : "r"(a), "r"(b), "r"(c)); return r; }
__device__ __forceinline__ uint32_t hfnma(uint32_t a, uint32_t b, uint32_t c) { uint32_t r; asm("{.reg .b32 n; neg.f16x2 n, %1; fma.rn.f16x2 %0, n, %2, %3;}" : "=r"(r) : "r"(a), "r"(b), "r"(c)); return r; }
__device__ __forceinline__ uint32_t hmul16(uint32_t a, uint32_t b) { uint32_t r; asm("mul.rn.f16x2 %0, %1, %2;" : "=r"(r) : "r"(a), "r"(b)); return r; }
template <int N> __device__ __forceinline__ void keepu(uint32_t (&d)[N]) {
#pragma unroll
  for (int i = 0; i < N; i++) asm volatile("" : "+r"(d[i])::"memory");
}
__device__ __forceinline__ void conv_m1(const ConvC& K, uint32_t (&u)[16], uint32_t l) {
  wg_fence();
  wgmma_hrs_n64<1>(u, K.a1[0][0], K.a1[0][1], K.a1[0][2], K.a1[0][3], dsc(l, 32), 0);
  wgmma_hrs_n64<1>(u, K.a1[1][0], K.a1[1][1], K.a1[1][2], K.a1[1][3], dsc(l + 16, 32), 1);
  wg_commit();
}
__device__ __forceinline__ void conv_s2(const ConvC& K, uint32_t (&u)[16], uint32_t (&Z)[2][8], uint32_t dfl) {
  uint32_t fr[8], fi[8];
#pragma unroll
  for (int c = 0; c < 8; c++) {
    const uint32_t r = hfma(K.wa[c & 1], u[2 * c + 1], u[2 * c]);
    fi[c] = hfma(K.wb[c & 1], r, u[2 * c + 1]);
    fr[c] = hfma(K.wa[c & 1], fi[c], r);
  }
  wg_fence();
#pragma unroll
  for (int p = 0; p < 2; p++) {
    wgmma_hrs_n32<0>(Z[p], fr[4 * p], fr[4 * p + 2], fr[4 * p + 1], fr[4 * p + 3], dsc(dfl, 32), 0);
    wgmma_hrs_n32<0>(Z[p], fi[4 * p], fi[4 * p + 2], fi[4 * p + 1], fi[4 * p + 3], dsc(dfl + 16, 32), 1);
  }
  wg_commit();
}
__device__ __forceinline__ void conv_win(const ConvC& K, const uint32_t (&X)[2][8], uint32_t (&W)[2][8]) {
#pragma unroll
  for (int b = 0; b < 4; b++)
#pragma unroll
    for (int c = 0; c < 2; c++) {
      const uint32_t xr = X[b >> 1][2 * c + (b & 1)], xi = X[b >> 1][4 + 2 * c + (b & 1)];
      const int a = b ? b - 1 : 0;
      W[b >> 1][2 * c + (b & 1)] = b ? hfnma(K.sg, X[a >> 1][4 + 2 * c + (a & 1)], xr) : hmul16(xr, 0x3C003C00u);
      W[b >> 1][4 + 2 * c + (b & 1)] = b ? hfma(K.sg, X[a >> 1][2 * c + (a & 1)], xi) : hmul16(xi, 0x3C003C00u);
    }
}
template <int p>
__device__ __forceinline__ void conv_pw(uint32_t (&X)[2][8], uint32_t (&H)[2][8], uint32_t (&V)[8], uint32_t dil) {
  uint32_t pr[2][2], pi[2][2];
#pragma unroll
  for (int jj = 0; jj < 2; jj++)
#pragma unroll
    for (int c = 0; c < 2; c++) {
      const int j = 2 * p + jj;
      uint32_t sr = 0, si = 0;
#pragma unroll
      for (int a = 0; a <= j; a++) {
        const int b = j - a;
        const uint32_t hr = H[a >> 1][2 * c + (a & 1)], hi = H[a >> 1][4 + 2 * c + (a & 1)];
        const uint32_t xr = X[b >> 1][2 * c + (b & 1)], xi = X[b >> 1][4 + 2 * c + (b & 1)];
        sr = a == 0 ? hmul16(hr, xr) : hfma(hr, xr, sr);
        si = a == 0 ? hmul16(hr, xi) : hfma(hr, xi, si);
        sr = hfnma(hi, xi, sr);
        si = hfma(hi, xr, si);
      }
      pr[jj][c] = sr; pi[jj][c] = si;
    }
  wg_fence();
  wgmma_hrs_n32<0>(V, pr[0][0], pr[1][0], pr[0][1], pr[1][1], dsc(dil, 32), 0);
  wgmma_hrs_n32<0>(V, pi[0][0], pi[1][0], pi[0][1], pi[1][1], dsc(dil + 16, 32), 1);
  wg_commit();
}
template <int p>
__device__ __forceinline__ void conv_it(const ConvC& K, uint32_t (&V)[8], uint32_t vst) {
#pragma unroll
  for (int jj = 0; jj < 2; jj++) {
    uint32_t wr[2], wi[2];
#pragma unroll
    for (int c = 0; c < 2; c++) {
      const uint32_t r = hfnma(K.wa[c], V[4 + 2 * c + jj], V[2 * c + jj]);
      wi[c] = hfnma(K.wb[c], r, V[4 + 2 * c + jj]);
      wr[c] = hfnma(K.wa[c], wi[c], r);
    }
    stsm4(vst + (2 * p + jj) * 2048, wr[0], wr[1], wi[0], wi[1]);
  }
}
__device__ __forceinline__ void conv_m4(uint32_t (&y)[8], uint32_t (&a)[4][4], uint32_t d4l) {
  wg_fence();
  wgmma_hrs_n32<0>(y, a[0][0], a[0][1], a[0][2], a[0][3], dsc(d4l, 64), 0);
#pragma unroll
  for (int s = 1; s < 4; s++) wgmma_hrs_n32<0>(y, a[s][0], a[s][1], a[s][2], a[s][3], dsc(d4l + s * 16, 64), 1);
  wg_commit();
}

struct Params {
  CUtensorMap tmX0, tmW, tmX, tmWo, tmWo1, tmK, tmV, tmQ, tmOA, tmOB;
  const __nv_bfloat16 *shift_k, *h, *D, *x, *w, *wo, *q;
  float *part, *kv;
  uint4* o;
  const uint32_t *thr, *img;
};

__global__ void __cluster_dims__(2, 1, 1) __launch_bounds__(384, 1) fused_kernel(const __grid_constant__ Params P) {
  extern __shared__ __align__(1024) uint8_t smem[];
  const uint32_t sb = __shfl_sync(~0u, smem_u32(smem), 0);
  const uint32_t bars = sb + OFF_BAR;
  const int tid = threadIdx.x, lane = tid & 31;
  const int warp = __shfl_sync(~0u, tid >> 5, 0);
  const int rank = blockIdx.x & 1, pc = blockIdx.x >> 1;
  const unsigned c7 = pc + 6, g7 = (c7 * 37) >> 8;
  const int mb = pc < 4 ? 4 + pc : pc < 36 ? (pc - 4) >> 3 : g7 - 2;
  const int hq = pc < 4 ? 0 : pc < 36 ? (pc - 4) & 7 : 1 + c7 - 7 * g7;
  const int cl = 8 * hq + mb;
  const int hp = 2 * hq + rank;
  const int rb = 2 * mb + (hq >> 2), cb = hq & 3;
#define BAR(i) (bars + 8 * (i))
#define OCNT(rb, hh) ((unsigned*)(P.o + (rb) * OBLK + 16 * 1024 + 8 * (hh)))
#define EPOCH (OCNT(rb, 2)[hp & 7])

  if (tid == 0) { STAMP(0, 0); GSTAMP(0, 30); }
  if (warp == 8) {
    if (elect_one()) {
      mbar_init(BAR(B_FULL1), 1);
      mbar_init(BAR(B_FIRST), 1);
      asm volatile("fence.mbarrier_init.release.cluster;" ::: "memory");
      mbar_expect(BAR(B_FIRST), STAGE_BYTES - 16384);
      tma2d(sb, &P.tmX0, 0, mb * 256, BAR(B_FIRST));
      tma2d(sb + 16384, &P.tmX0, 0, mb * 256 + 128, BAR(B_FIRST));
      tma3d(sb + 32768, &P.tmW, hp * 64, 0, 0, BAR(B_FIRST));
    }
    if (lane == 0) STAMP(3, 21);
  } else if (lane == 0) {
    const int wi = warp - (warp > 8);
#pragma unroll
    for (int r = 0; r < 6; r++)
      if (r < 5 || wi < B_COUNT - 56) mbar_init(BAR(1 + 11 * r + wi), ((uint32_t)(bar_counts(r) >> (4 * wi)) & 15) + 1);
    asm volatile("fence.mbarrier_init.release.cluster;" ::: "memory");
  }
  if (tid == 0) STAMP(2, 6);
  asm volatile("barrier.cluster.arrive.relaxed.aligned;\nbarrier.cluster.wait.aligned;" ::: "memory");
  if (warp == 8 && elect_one()) {
    mbar_expect(BAR(B_FULL1), 16384);
    tma2d_mc(sb + 8192 + rank * 16384, &P.tmX0, 0, mb * 256 + 64 + rank * 128, BAR(B_FULL1));
  }
  if (tid == 256) STAMP(2, 7);

  if (warp < 8) {
    asm volatile("setmaxnreg.inc.sync.aligned.u32 224;");
    const int wg = warp >> 2, w = warp & 3, g = lane >> 2, q = lane & 3, t = tid & 127;
    const bool elect = (t == 0);
    const uint32_t s16 = (sb & 0x3FFFF) >> 4;
    uint32_t pq[2][16], ux[16], uh[16], X[4][2][8], H[4][2][8];
    ConvC K;
    const uint32_t dfl = s16 + (OFF_F2F >> 4) + (8 << 16), dil = s16 + (OFF_F2I >> 4) + (8 << 16), d4l = s16 + (OFF_F4 >> 4) + (8 << 16);
    const uint32_t xl = s16 + (OFF_XT >> 4) + 4 * wg * (XT_STRIDE >> 4) + (8 << 16);
    const uint32_t hl = s16 + (OFF_H >> 4) + wg * 512 + (8 << 16);
    {
      float acc[2][96];
      if (SPLIT0) {
#pragma unroll
        for (int mt = 0; mt < 2; mt++) {
          mbar_wait(BAR(mt ? B_FULL1 : B_FIRST), 0);
          if (mt == 0 && elect) { STAMP(wg, 1); GSTAMP(wg, 26); }
          wg_fence();
#pragma unroll
          for (int ks = 0; ks < 4; ks++)
            wgmma_ss_n192<0, 1>(acc[mt], dsc(s16 + wg * 1024 + mt * 512 + (1 << 16) + ks * 2, SW128), dsc(s16 + 2048 + (512 << 16) + ks * 128, SW128), ks != 0);
        }
        wg_commit();
      }
      int st = SPLIT0 ? 1 : 0, ph = 0;
#pragma unroll 1
      for (int kb = SPLIT0 ? 1 : 0; kb < 14; kb++) {
        mbar_wait(BAR(B_FULL1 + st), ph);
        if (kb == 0 && elect) { STAMP(wg, 1); GSTAMP(wg, 26); }
        if (kb == 8 && elect) { STAMP(wg, 16); GSTAMP(wg, 25); }
        const uint32_t da = s16 + st * (STAGE_BYTES >> 4) + wg * 1024 + (1 << 16);
        const uint32_t db = s16 + st * (STAGE_BYTES >> 4) + 2048 + (512 << 16);
        wg_fence();
#pragma unroll
        for (int ks = 0; ks < 4; ks++) {
          wgmma_ss_n192<0, 1>(acc[0], dsc(da + ks * 2, SW128), dsc(db + ks * 128, SW128), (kb | ks) != 0);
          wgmma_ss_n192<0, 1>(acc[1], dsc(da + 512 + ks * 2, SW128), dsc(db + ks * 128, SW128), (kb | ks) != 0);
        }
        wg_commit();
        wg_wait<1>();
        if (kb > 0 && t < 2) mbar_arrive_cl(BAR(B_EMPTY1 + (st == 0 ? 2 : st - 1)), t);
        if (++st == 3) { st = 0; ph ^= 1; }
      }
#define TAIL_MMA(mt, stage) do { wg_fence(); _Pragma("unroll") for (int ks = 0; ks < 4; ks++) \
        wgmma_ss_n192<0, 1>(acc[mt], dsc(s16 + (stage) * (STAGE_BYTES >> 4) + wg * 1024 + (mt) * 512 + (1 << 16) + ks * 2, SW128), \
                            dsc(s16 + (stage) * (STAGE_BYTES >> 4) + 2048 + (512 << 16) + ks * 128, SW128), 1); wg_commit(); } while (0)
      mbar_wait(BAR(B_FULL1 + 2), 0);
      TAIL_MMA(0, 2);
      wg_wait<1>();
      if (elect) mbar_arrive(BAR(B_SFREE));
      mbar_wait(BAR(B_FULL1 + 0), 1);
      TAIL_MMA(0, 0);
      TAIL_MMA(1, 2);
      const uint32_t lrow = sb + wg * 16384 + (16 * w + 8 * ((lane >> 3) & 1) + (lane & 7)) * 128 + (((lane >> 4) ^ (lane & 7)) << 4);
#define E1K(mt, i) do { if (opaque_true()) { _Pragma("unroll") for (int j = (i); j < (i) + 2; j++) { \
          const float* a = &acc[mt][32 + 8 * j]; const float* b = a + 32; const uint32_t o = (lrow ^ (j * 32)) + (mt) * 8192; \
          stsm4(o + 2 * STAGE_BYTES, pk2(b[0], b[1]), pk2(b[2], b[3]), pk2(b[4], b[5]), pk2(b[6], b[7])); \
          stsm4(o, phi2(a[0], a[1]), phi2(a[2], a[3]), phi2(a[4], a[5]), phi2(a[6], a[7])); } } } while (0)
#define E1Q(mt) do { if (opaque_true()) { _Pragma("unroll") for (int i = 0; i < 16; i++) pq[mt][i] = phi2(acc[mt][2 * i], acc[mt][2 * i + 1]); } } while (0)
#define LOAD_K() do { const uint4* ct = (const uint4*)P.thr + t; \
        _Pragma("unroll") for (int s = 0; s < 2; s++) { const uint4 u = ld_na4(ct + s * 128); K.a1[s][0] = u.x; K.a1[s][1] = u.y; K.a1[s][2] = u.z; K.a1[s][3] = u.w; } \
        const uint4 u = ld_na4(ct + 2 * 128); K.wa[0] = u.x; K.wa[1] = u.y; K.wb[0] = u.z; K.wb[1] = u.w; \
        K.sg = (lane & 4) ? 0xBC00BC00u : 0x3C003C00u; } while (0)
#define PK_READY(mt) do { fence_async(); __syncwarp(); if (lane == 0) mbar_arrive(BAR(B_PKRDY + (mt))); } while (0)
      wg_wait<1>();
      keep(acc[0]);
      if (elect) STAMP(wg, 18);
      E1K(0, 0);
      TAIL_MMA(1, 0);
      E1K(0, 2);
      if (elect) STAMP(wg, 19);
      PK_READY(0);
      wg_wait<0>();
      keep(acc[1]);
      if (elect) mbar_arrive(BAR(B_G1DONE));
      asm volatile("setmaxnreg.dec.sync.aligned.u32 %0;" ::"n"(RC));
      if (elect) { STAMP(wg, 2); GSTAMP(wg, 27); }
      E1K(1, 0);
      if (elect) STAMP(wg, 20);
      E1K(1, 2);
      if (elect) STAMP(wg, 21);
      PK_READY(1);
      if (elect) STAMP(wg, 3);
      LOAD_K();
      if (elect) STAMP(wg, 4);
      E1Q(0);
      E1Q(1);
      if (elect) STAMP(wg, 17);
      mbar_wait(BAR(B_H), 0);
      conv_m1(K, ux, xl);
      conv_m1(K, uh, hl);
      wg_wait<1>(); keepu(ux);
      if (lane == 0) mbar_arrive_cl(BAR(B_XFREE + 4 * wg), rank ^ 1);
      conv_s2(K, ux, X[0], dfl);
      wg_wait<1>(); keepu(uh);
      conv_s2(K, uh, H[0], dfl);
    }
    if (elect) STAMP(wg, 5);
    float acc[64];
#define G2_MMA(da, db, first) do { wg_fence(); _Pragma("unroll") for (int ks = 0; ks < 4; ks++) \
        wgmma_ss_n128<0, 1>(acc, dsc((da) + ks * 2, SW128), dsc((db) + ks * 128, SW128), ks || !(first)); wg_commit(); } while (0)
    const uint32_t a0 = s16 + wg * 512 + (1 << 16), b0 = s16 + (512 << 16);
    uint32_t cons = mapa(BAR(B_CONS2 - 1 + G2E), t & 1);
    const bool rel = __shfl_sync(~0u, t, lane) < 2;
    {
      uint32_t vst = sb + wg * 8192 + w * 512 + lane * 16, vld = sb + wg * 8192 + w * 2048 + lane * 16;
      uint32_t ya = mapa(sb + OFF_XT + 4 * wg * XT_STRIDE + (2 * rank + (w & 1)) * 1024 + lane * 16, w >> 1);
      const uint32_t ybar = mapa(BAR(B_Y), w >> 1);
      asm volatile("" : "+r"(vst), "+r"(vld), "+r"(ya));
      uint32_t W[2][8], V0[8], V1[8], y[8], a[4][4];
      uint4 ov[4];
      uint4* const ot = P.o + (2 * mb + wg) * OBLK + hq * 1024 + (16 * w + g) * 8 + ((4 * rank + q) ^ g);
#define YOUT(i) do { if ((w >> 1) == rank) { \
          asm volatile("st.shared.v4.b32 [%0], {%1,%2,%3,%4};" ::"r"(ya + (i) * XT_STRIDE), "r"(y[0]), "r"(y[2]), "r"(y[4]), "r"(y[6]) : "memory"); \
          asm volatile("st.shared.v4.b32 [%0], {%1,%2,%3,%4};" ::"r"(ya + (i) * XT_STRIDE + 512), "r"(y[1]), "r"(y[3]), "r"(y[5]), "r"(y[7]) : "memory"); \
        } else { \
          mbar_wait(BAR(B_XFREE + 4 * wg + (i)), 0); \
          st_async4(ya + (i) * XT_STRIDE, y[0], y[2], y[4], y[6], ybar); \
          st_async4(ya + (i) * XT_STRIDE + 512, y[1], y[3], y[5], y[7], ybar); } } while (0)
      auto ocalc = [&](const int hh) {
        if (hh == 0) {
          if (elect) STAMP(wg, 8);
          mbar_wait(BAR(B_KV), 0);
          if (elect) STAMP(wg, 9);
        } else mbar_wait(BAR(B_KV1), 0);
        float oa[2][20];
        wg_fence();
#pragma unroll
        for (int m = 0; m < 4; m++) {
          const uint32_t* p = &pq[m & 1][8 * hh + 4 * (m >> 1)];
          wgmma_rs_n40<1>(oa[m & 1], p[0], p[1], p[2], p[3], dsc(s16 + (OFF_KVB >> 4) + hh * 160 + (m >> 1) * 16 + (8 << 16), 32), m >> 1);
        }
        wg_commit();
        wg_wait<0>();
#pragma unroll
        for (int mt = 0; mt < 2; mt++) {
          float (&o)[20] = oa[mt];
          keep(o);
          const uint32_t den = hadd(pk2(o[16], o[18]), 0x35863586u);
#pragma unroll
          for (int r = 0; r < 2; r++) {
            const float ri = rcp_fast(__uint_as_float(r ? (den & 0xFFFF0000u) : (den << 16)));
            uint4 u;
            u.x = pk2(o[2 * r] * ri, o[2 * r + 1] * ri);
            u.y = pk2(o[4 + 2 * r] * ri, o[5 + 2 * r] * ri);
            u.z = pk2(o[8 + 2 * r] * ri, o[9 + 2 * r] * ri);
            u.w = pk2(o[12 + 2 * r] * ri, o[13 + 2 * r] * ri);
            if (hh == 0) st_cg4(ot + (64 * mt + 8 * r) * 8, u); else ov[2 * mt + r] = u;
          }
        }
        if (hh == 0) {
          __syncwarp();
          if (lane == 0) mbar_arrive(BAR(B_ODONE));
          if (elect) STAMP(wg, 10);
        }
      };
      auto trickle = [&](const int qs) {
        const int m = qs - 2 * (OCH + O1D) - (TRICK - 1);
        if (m >= 0 && m < 4) {
          st_cg4(ot + 8 * 1024 + (64 * (m >> 1) + 8 * (m & 1)) * 8, ov[m]);
          if (m == 3) { __syncwarp(); if (lane == 0) mbar_arrive(BAR(B_ODONE1)); }
        }
      };
#pragma unroll
      for (int i = 0; i < 4; i++) {
        const bool nx = i < 3;
        const int n = nx ? i + 1 : i;
        const uint32_t vo = (i & 1) ? OFF_H + (i >> 1) * 16384 : OFF_VP;
        if (2 * i == OCH) ocalc(0);
        if (2 * i == OCH + O1D) ocalc(1);
        if (nx) {
          conv_m1(K, ux, xl + n * (XT_STRIDE >> 4));
          conv_m1(K, uh, hl + (n >> 1) * 1024 + (n & 1) * 256);
        }
        if (2 * i != OCH && 2 * i != OCH + O1D) { if (nx) { if (i > 0) wg_wait<3>(); else wg_wait<2>(); } else wg_wait<1>(); }
        keepu(X[i][0]); keepu(X[i][1]); keepu(H[i][0]); keepu(H[i][1]);
        conv_win(K, X[i], W);
        trickle(4 * i);
        conv_pw<0>(W, H[i], V0, dil);
        conv_pw<1>(W, H[i], V1, dil);
        trickle(4 * i + 1);
        wg_wait<2>();
        if (i > 0) { keepu(y); YOUT(i - 1); }
        if (2 * i + 1 == OCH) ocalc(0);
        if (2 * i + 1 == OCH + O1D) ocalc(1);
        if (nx) {
          keepu(ux); keepu(uh);
          if (lane == 0) mbar_arrive_cl(BAR(B_XFREE + 4 * wg + n), rank ^ 1);
          conv_s2(K, ux, X[n], dfl);
          wg_wait<1>();
        } else wg_wait<0>();
        keepu(V0); keepu(V1);
        if (G2E && G2P == 0 && i == 3) { mbar_wait(BAR(B_FULL2), 0); G2_MMA(a0 + (SLOT_A & 15) * 1024, b0 + (SLOT_B & 15) * 1024, true); }
        trickle(4 * i + 2);
        if (i == 0) mbar_wait(BAR(B_H2), 0);
        conv_it<0>(K, V0, vst + vo);
        conv_it<1>(K, V1, vst + vo);
        if (G2E && G2P == 1 && i == 3) { mbar_wait(BAR(B_FULL2), 0); G2_MMA(a0 + (SLOT_A & 15) * 1024, b0 + (SLOT_B & 15) * 1024, true); }
        bar_sync(1 + wg);
#pragma unroll
        for (int s = 0; s < 4; s++) ldsm4t(a[s], vld + vo + s * 512);
        if (nx) conv_s2(K, uh, H[n], dfl);
        conv_m4(y, a, d4l);
        trickle(4 * i + 3);
        if (i > 0 && lane < 2) mbar_arrive_cl(BAR(B_AFREE + i - 1), lane);
        if (elect && i < 3) STAMP(wg, i < 2 ? 6 + i : 9 + i);
      }
      if (G2E && G2P == 2) { mbar_wait(BAR(B_FULL2), 0); G2_MMA(a0 + (SLOT_A & 15) * 1024, b0 + (SLOT_B & 15) * 1024, true); wg_wait<1>(); }
      else wg_wait<0>();
      keepu(y);
      if (G2E && G2P < 2 && rel) asm volatile("mbarrier.arrive.shared::cluster.b64 _, [%0];" ::"r"(cons) : "memory");
      YOUT(3);
      __syncwarp();
      if (lane == 0) mbar_arrive(BAR(B_Y));
      if (elect) STAMP(wg, 12);
    }
    {
      uint64_t ta = SLOT_A >> (4 * G2E), tb = SLOT_B >> (4 * G2E);
      uint32_t da = a0 + ((uint32_t)ta & 15) * 1024, db = b0 + ((uint32_t)tb & 15) * 1024, fb = BAR(B_FULL2 + G2E);
#pragma unroll 1
      for (int kb = G2E; kb < HOLD2; kb++) {
        mbar_wait(fb, 0);
        G2_MMA(da, db, kb == 0);
        ta >>= 4; tb >>= 4;
        da = a0 + ((uint32_t)ta & 15) * 1024; db = b0 + ((uint32_t)tb & 15) * 1024; fb += 8;
        asm volatile("" : "+r"(da), "+r"(db));
        wg_wait<1>();
        if ((kb > G2E || (G2E && G2P == 2)) && kb < 12 && rel) asm volatile("mbarrier.arrive.shared::cluster.b64 _, [%0];" ::"r"(cons) : "memory");
        cons += 8;
      }
#pragma unroll
      for (int kb = HOLD2; kb < 16; kb++) {
        if (wg == 1) mbar_wait(BAR(B_FULL2 + kb), 0);
        else if (kb == HOLD2) asm volatile("bar.sync 3, 256;" ::: "memory");
        G2_MMA(a0 + ((SLOT_A >> (4 * kb)) & 15) * 1024, b0 + ((SLOT_B >> (4 * kb)) & 15) * 1024, false);
      }
      if (wg == 1) asm volatile("bar.arrive 3, 256;" ::: "memory");
      const uint32_t stg = sb + wg * 8192 + w * 2048, so0 = ((SLOT_A >> 56) & 15) * 16384, so1 = ((SLOT_A >> 60) & 15) * 16384;
      const uint32_t lrow = stg + (8 * ((lane >> 3) & 1) + (lane & 7)) * 128 + (((lane >> 4) ^ (lane & 7)) << 4);
      const int col = 1024 + 256 * cb + 128 * rank, row = 128 * rb + 64 * wg + 16 * w;
      wg_wait<0>();
      keep(acc);
      if (elect) { STAMP(wg, 14); GSTAMP(wg, 29); }
#pragma unroll
      for (int cp = 0; cp < 8; cp++) {
        const float* a = &acc[8 * cp];
        stsm4((lrow ^ ((cp & 3) * 32)) + (cp >> 2 ? so1 : so0), pk2(a[0], a[1]), pk2(a[2], a[3]), pk2(a[4], a[5]), pk2(a[6], a[7]));
        if ((cp & 3) == 3) {
          fence_async();
          __syncwarp();
          if (elect_one()) tma2d_st(&P.tmOB, stg + (cp >> 2 ? so1 : so0), col + (cp >> 2) * 64, row);
        }
      }
      asm volatile("cp.async.bulk.commit_group;\ncp.async.bulk.wait_group.read 0;" ::: "memory");
      if (elect) {
        STAMP(wg, 15); GSTAMP(wg, 31); PDUMP(wg); if (wg == 0) PDUMP(2);
      }
    }
  } else {
    asm volatile("setmaxnreg.dec.sync.aligned.u32 56;");
    const int hw = warp - 9, g = lane >> 2, q = lane & 3;
#define sbar (bars + 8 * (B_STG - 18) + 16 * warp)
    if (warp == 8) {
      if (D1) __nanosleep(D1);
      int st = 1, pp = 1;
      const uint8_t* pfx = (const uint8_t*)P.x + (mb * 256 + hp * 16 + (lane & 15)) * 2048;
      const uint8_t* pfw = (const uint8_t*)P.w + (mb * 8 + (lane & 7)) * 6144 + (lane >> 3) * 2048 + hp * 128;
#pragma unroll 1
      for (int kb = 1; kb < 16; kb++) {
        if (kb >= 3) mbar_wait(BAR(B_EMPTY1 + st), pp);
        const uint32_t sa = sb + st * STAGE_BYTES;
        if (elect_one()) {
          mbar_expect(BAR(B_FULL1 + st), STAGE_BYTES);
          tma2d_mc(sa + rank * 16384, &P.tmX, kb * 64, mb * 256 + rank * 128, BAR(B_FULL1 + st));
          tma3d(sa + 32768, &P.tmW, hp * 64, kb * 64, 0, BAR(B_FULL1 + st));
        }
        if (kb == 1 && lane == 0) STAMP(2, 24);
        if (PFD && kb >= 2) {
#pragma unroll 1
          for (int j = kb == 2 ? 3 : kb + PFD; j <= kb + PFD && j < 16; j++) {
            if (lane < 16) asm volatile("prefetch.global.L2 [%0];" ::"l"(pfx + j * 128));
            if (lane < 24) asm volatile("prefetch.global.L2 [%0];" ::"l"(pfw + j * (64 * 6144)));
          }
          if (kb >= QPF && kb < QPF + 8) asm volatile("prefetch.global.L2 [%0];" ::"l"((const uint8_t*)P.q + (blockIdx.x * 256 + (kb - QPF) * 32 + lane) * 128));
          if (kb >= 4)
            asm volatile("prefetch.global.L2 [%0];" ::"l"(kb < 12 ? (const uint8_t*)P.h + ((2 * cl + rank) * 256 + (kb - 4) * 32 + lane) * 128
                                                                  : (const uint8_t*)P.wo + (blockIdx.x * 128 + (kb - 12) * 32 + lane) * 128));
        }
        if (++st == 3) { st = 0; pp ^= 1; }
      }
      if (lane == 0) STAMP(2, 1);
    } else {
      {
        const uint32_t clk0 = __shfl_sync(~0u, (uint32_t)clock(), 0), stg = sb + OFF_STG + hw * STG_STRIDE;
        const unsigned epoch = __shfl_sync(~0u, EPOCH, 0);
        const uint32_t tag = ~epoch & 1;
        uint32_t tap[2][4];
#pragma unroll
        for (int cg = 0; cg < 2; cg++) {
          const uint2 u = __ldg((const uint2*)(P.shift_k + (16 * cl + 8 * cg + g) * 4));
          tap[cg][0] = __byte_perm(u.x, 0, 0x1010); tap[cg][1] = __byte_perm(u.x, 0, 0x3232);
          tap[cg][2] = __byte_perm(u.y, 0, 0x1010); tap[cg][3] = __byte_perm(u.y, 0, 0x3232);
        }
        if (hw == 0 && lane < 8) *(float*)(smem + OFF_D + 4 * lane) = __bfloat162float(P.D[16 * cl + 8 * rank + lane]);
        if (hw == 1 && lane < 24) asm volatile("prefetch.global.L2 [%0];" ::"l"(P.thr + (lane + 24 * rank) * 32));
        if (hw == 0 && elect_one()) {
          *(volatile unsigned*)(smem + OFF_EPOCH) = epoch;
          mbar_expect(BAR(B_XRAW), 16384);
          mbar_expect(BAR(B_Y), 16384 + 64);
        }
#pragma unroll 1
        for (int i = hw * 32 + lane; i < 528; i += 96) st_tag4(P.part + (hp * 8 + mb) * 2176 + 4 * i, 0.f, 0.f, 0.f, 0.f, tag ^ 1);
        if (hw < 2 || lane < 2) st_tag4(P.kv + hp * 2176 + (4 * (hw < 2 ? 64 * mb + 32 * hw + lane : 512 + 8 * (mb & 1) + (mb & 6) + lane)), 0.f, 0.f, 0.f, 0.f, tag ^ 1);
        if (lane == 0) STAMP(3, hw);
        const uint32_t xo = sb + OFF_XT + g * XT_STRIDE + rank * 2048 + q * 4;
        const int krow = 8 + (lane & 7) - (lane >> 3);
        const uint32_t ka = stg + krow * 32 + ((krow & 4) << 2), va = stg + 2304 + lane * 32 + ((lane & 4) << 2);
        int ph = 0, b = 0;
#pragma unroll 1
        for (int ci = hw - 3; ci < 16; ci += 3) {
          const uint32_t bo = b ? OFF_F2F - OFF_STG : 0, bn = b ? 0 : OFF_F2F - OFF_STG;
          if (ci + 3 < 16) {
            while (__any_sync(~0u, (uint32_t)clock() - clk0 < HSTART + (ci + 3) * PACE)) __nanosleep(64);
            if (elect_one()) {
              mbar_expect(sbar + 8 * (b ^ 1), 2304 + 2048);
              tma2d(stg + bn, &P.tmK, 16 * cl, 1024 * rank + 64 * (ci + 3) - 8, sbar + 8 * (b ^ 1));
              tma2d(stg + bn + 2304, &P.tmV, 16 * cl, 1024 * rank + 64 * (ci + 3), sbar + 8 * (b ^ 1));
            }
          }
          if (ci >= 0) {
            mbar_wait(sbar + 8 * b, (ph >> b) & 1);
            ph ^= 1 << b;
#pragma unroll 1
            for (int grp = 0; grp < 2; grp++) {
#pragma unroll
              for (int cg = 0; cg < 2; cg++) {
                const uint32_t dst = mapa(xo + (ci >> 3) * 1024 + ((ci & 7) * 4 + 2 * grp) * 16, cg), xbar = mapa(BAR(B_XRAW), cg);
                uint32_t vv[4], kk[4][4];
                ldsm4t(vv, (va ^ (cg * 16)) + bo + grp * 1024);
#pragma unroll
                for (int rg = 0; rg < 4; rg++) ldsm4t(kk[rg], (ka ^ (cg * 16)) + bo + grp * 1024 + rg * 256);
#pragma unroll
                for (int rg = 0; rg < 4; rg++)
                  vv[rg] = hmul(hadd(hadd(hadd(hmul(kk[rg][3], tap[cg][3]), hmul(kk[rg][2], tap[cg][2])), hmul(kk[rg][1], tap[cg][1])), hmul(kk[rg][0], tap[cg][0])), vv[rg]);
                if (cg == rank) {
#pragma unroll
                  for (int rg = 0; rg < 4; rg++) asm volatile("st.shared.b32 [%0], %1;" ::"r"(dst + (rg & 1) * 512 + (rg >> 1) * 16), "r"(vv[rg]) : "memory");
                } else {
#pragma unroll
                  for (int rg = 0; rg < 4; rg++) st_async(dst + (rg & 1) * 512 + (rg >> 1) * 16, vv[rg], xbar);
                }
              }
            }
          }
          b ^= 1;
        }
      }
      if (lane == 0 && hw == 0) STAMP(3, 3);
      asm volatile("bar.sync 4, 96;" ::: "memory");
      if (hw == 0 && elect_one()) { mbar_expect(BAR(B_XT), 10240); bulk_ld(sb + OFF_F2F, P.img, 10240, BAR(B_XT)); }
      mbar_wait(BAR(B_XRAW), 0);
    }
    int e1 = 0;
#pragma unroll 1
    for (int n = hw < 0 ? 3 : 0; n < 4; n++) {
      const bool isH = n >= 3;
      const int c = isH ? (warp & 1) + 2 * (warp & 2) : hw + 3 * n;
      if (c < 8) {
        int ln;
        asm volatile("mov.u32 %0, %%laneid;" : "=r"(ln));
        uint8_t* dst = smem + (isH ? OFF_H + (c & 2) * 8192 + (c >> 2) * 8192 + (c & 1) * 4096 : OFF_XT + c * XT_STRIDE) + ((ln >> 4) * 512 + (ln & 15) * 16);
        const uint8_t* src0 = isH ? (const uint8_t*)P.h + (16 * cl + 8 * rank + c) * 4096 + ((ln & 15) * 32 + (ln & 16)) : dst;
        const uint8_t* src1 = src0 + (isH ? 512 : 256);
        uint32_t v[32];
#pragma unroll
        for (int i = 0; i < 8; i++) {
          const uint4 u = *(const uint4*)(((i & 1) ? src1 : src0) + (i >> 1) * 1024);
          v[4 * i] = u.x; v[4 * i + 1] = u.y; v[4 * i + 2] = u.z; v[4 * i + 3] = u.w;
        }
        if (isH) mbar_wait(BAR(B_XT), 0);
        const float f0 = __uint_as_float(v[0] << 16) + ((isH && ln == 0) ? *(const float*)(smem + OFF_D + 4 * c) : 0.f);
        const int e = norm_exp(v, f0);
        norm_cvt(v, f0, e);
        if (isH) mbar_wait(BAR(B_SFREE), 0);
        else if (ln == 0) smem[OFF_EX + c] = e;
        e1 = e;
#pragma unroll
        for (int i = 0; i < 8; i++)
          *(uint4*)(dst + (i >> 1) * 1024 + (i & 1) * 256) = make_uint4(v[4 * i], v[4 * i + 1], v[4 * i + 2], v[4 * i + 3]);
        if (n < 2 && elect_one()) {
          if (n == 0) mbar_expect(sbar, 4096);
          tma3d(sb + OFF_STG + 2048 * c, &P.tmQ, 16 * cl, 64 * rank, 2 * c, sbar);
        }
      }
      if (n >= 2) {
        fence_async();
        __syncwarp();
        if (lane == 0) { mbar_arrive(BAR(isH ? B_H : B_XT)); STAMP(3, (isH ? 17 : 13) + hw); }
      }
    }
#define SLOT(tab, kb) (sb + ((uint32_t)((tab) >> (4 * (kb))) & 15) * 16384)
#define KT(kb) (!OLOC ? (kb) : (kb) == 0 ? hq : (kb) == hq ? 0 : (kb))
#define LOAD_B(kb) tma4d(SLOT(SLOT_B, kb), &P.tmWo, 0, ((kb) >> 3) * 32, 2 * (KT(kb) & 7), 4 * cb + 2 * rank, BAR(B_FULL2 + (kb)))
#define LOAD_A(kb) bulk_ld_mc(SLOT(SLOT_A, kb) + rank * 8192, P.o + rb * OBLK + KT(kb) * 1024 + rank * 512, 8192, BAR(B_FULL2 + (kb)))
    asm volatile("setmaxnreg.inc.sync.aligned.u32 %0;" ::"n"(504 - 2 * RC));
    {
    int tid;
    asm volatile("mov.u32 %0, %%tid.x;" : "=r"(tid));
    const int lane = tid & 31, g = lane >> 2, q = lane & 3;
    const unsigned epoch = *(volatile unsigned*)(smem + OFF_EPOCH);
    const uint32_t tag = ~epoch & 1;
    const int pi = hw < 2 ? 64 * mb - 288 + tid : 512 + 8 * (mb & 1) + (mb & 6) + (lane & 1);
    const float* psrc = P.part + hp * 8 * 2176 + 4 * pi;
    uint4 f[8];
    {
      const uint32_t s16 = (sb & 0x3FFFF) >> 4;
      const int t = tid & 127, c = 2 + (warp & 1) + 2 * (warp & 2);
      const uint4* hp4 = (const uint4*)(P.h + (16 * cl + 8 * rank + c) * 2048) + ((lane & 15) * 2 + (lane >> 4));
      uint32_t v[32];
#pragma unroll
      for (int i = 0; i < 8; i++) { const uint4 u = ld_na4(hp4 + i * 32); v[4 * i] = u.x; v[4 * i + 1] = u.y; v[4 * i + 2] = u.z; v[4 * i + 3] = u.w; }
      float kva[36];
#pragma unroll
      for (int mt = 0; mt < 2; mt++) {
        mbar_wait(BAR(B_PKRDY + mt), 0);
        wg_fence();
#pragma unroll
        for (int ks = 0; ks < 8; ks++) {
          const uint32_t o = (ks >> 2) * 1024 + mt * 512 + (ks & 3) * 128, vb = (2 * STAGE_BYTES >> 4) + o;
          wgmma_ss_n72<1, 1>(kva, dsc(s16 + o + (1 << 16), SW128), dsc(s16 + vb + (((OFF_ONES >> 4) - vb) << 16), SW128), (mt | ks) != 0);
        }
        wg_commit();
        if (mt == 0 && hw < 0) {
          mbar_wait(BAR(B_G1DONE), 0);
          if (elect_one()) {
#pragma unroll
            for (int kb = 0; kb < BEARLY; kb++) { mbar_expect(BAR(B_FULL2 + kb), 16384); LOAD_B(kb); }
          }
        }
      }
      float* pdst = P.part + (hp * 8 + mb) * 2176 + t * 4;
      float* zdst = P.part + (hp * 8 + mb) * 2176 + 2048 + (t >> 1);
      asm volatile("" : "+l"(pdst), "+l"(zdst));
      wg_wait<0>();
      keep(kva);
      if (hw < 1) {
#pragma unroll
        for (int c = 0; c < 4; c++) st_tag4(pdst + c * 512, kva[4 * c], kva[4 * c + 1], kva[4 * c + 2], kva[4 * c + 3], tag);
      } else {
#pragma unroll
        for (int c = 4; c < 8; c++) st_tag4(pdst + (c - 4) * 512, kva[4 * c], kva[4 * c + 1], kva[4 * c + 2], kva[4 * c + 3], tag);
      }
      const float z2 = __shfl_down_sync(~0u, kva[32], 4), z3 = __shfl_down_sync(~0u, kva[34], 4);
      if (!(lane & 7)) st_tag4(zdst, kva[32], kva[34], z2, z3, tag);
      if (lane == 0) mbar_arrive(BAR(B_PKFREE));
      const uint32_t cst = clock();
      if (hw == 0 && lane == 0) STAMP(3, 24);
      const float f0 = __uint_as_float(v[0] << 16) + (lane == 0 ? *(const float*)(smem + OFF_D + 4 * c) : 0.f);
      const int e = norm_exp(v, f0);
      norm_cvt(v, f0, e);
      if (hw >= 0) {
        while (__any_sync(~0u, (uint32_t)clock() - cst < PD1)) __nanosleep(20);
        if (hw == 0 && lane == 0) STAMP(3, 20);
#pragma unroll
        for (int p = 0; p < 8; p++) f[p] = ld_rlx4(psrc + p * 2176);
      }
      uint8_t* dst = smem + OFF_H + 16384 + (warp & 3) * 4096 + (lane >> 4) * 512 + (lane & 15) * 16;
#pragma unroll
      for (int i = 0; i < 8; i++)
        *(uint4*)(dst + (i >> 1) * 1024 + (i & 1) * 256) = make_uint4(v[4 * i], v[4 * i + 1], v[4 * i + 2], v[4 * i + 3]);
      if (lane < 4) {
        const int cc = c - (lane & 2);
        st_async(mapa(sb + OFF_SCALE + (8 * rank + cc) * 4, lane & 1), min(max(((lane & 2) ? e1 : e) + smem[OFF_EX + cc] - 124, 1), 254) << 23, mapa(BAR(B_Y), lane & 1));
      }
    }
#define H2_READY() do { fence_async(); __syncwarp(); if (lane == 0) mbar_arrive(BAR(B_H2)); } while (0)
    if (warp == 8) {
      H2_READY();
      mbar_wait(BAR(B_PKFREE), 0);
      {
        const uint32_t c0 = clock();
#pragma unroll 1
        for (int i = 0; i < 2 * NPRE - 2 * BEARLY; i++) {
          const int kb = (i >> 1) + BEARLY;
          while (__any_sync(~0u, (uint32_t)clock() - c0 < i * BPACE)) __nanosleep(32);
          if (elect_one()) {
            if (!(i & 1)) mbar_expect(BAR(B_FULL2 + kb), 16384);
            tma4d(SLOT(SLOT_B, kb) + (i & 1) * 8192, &P.tmWo1, 0, 0, 2 * KT(kb), 4 * cb + 2 * rank + (i & 1), BAR(B_FULL2 + kb));
            if (i == 0) mbar_expect(BAR(B_Q), 8192);
            if (i < 4) tma3d(sb + OFF_SPARE + 2048 * i, &P.tmQ, 16 * cl, 64 * rank + 32 * (i >> 1), 2 * ((i + 6) & 7), BAR(B_Q));
          }
        }
      }
      if (lane == 0) STAMP(2, 2);
      if (OLOC) {
        if (elect_one()) mbar_expect(BAR(B_FULL2), 16384);
        mbar_wait(BAR(B_OLOC), 0);
        asm volatile("fence.acquire.cluster;\nfence.proxy.async.global;" ::: "memory");
        if (elect_one()) LOAD_A(0);
      }
      mbar_wait(BAR(B_AFREE), 0);
      if (elect_one()) mbar_expect(BAR(B_FULL2 + OLOC), 16384);
      {
        const uint32_t dst = SLOT(SLOT_A, OLOC) + rank * 8192;
        const uint4* src = P.o + rb * OBLK + KT(OLOC) * 1024 + rank * 512;
        poll_ge(OCNT(rb, 0), 16 * (epoch + 1));
        asm volatile("fence.proxy.async.global;" ::: "memory");
        if (lane == 0) STAMP(2, 3);
        if (elect_one()) bulk_ld_mc(dst, src, 8192, BAR(B_FULL2 + OLOC));
        if (lane == 0) STAMP(3, 23);
      }
#pragma unroll 1
      for (int kb = 1 + OLOC; kb < NPRE; kb++) {
        mbar_wait(BAR(kb < 4 ? B_AFREE + kb - 1 : B_CONS2), 0);
        if (elect_one()) { mbar_expect(BAR(B_FULL2 + kb), 16384); LOAD_A(kb); }
      }
#pragma unroll 1
      for (int kb = NPRE; kb < 16; kb++) {
        mbar_wait(BAR(B_CONS2 + kb - 5), 0);
        if (kb == 8) mbar_wait(BAR(B_O1RDY), 0);
        if (elect_one()) { mbar_expect(BAR(B_FULL2 + kb), 32768); LOAD_A(kb); LOAD_B(kb); }
      }
      if (lane == 0) { EPOCH = epoch + 1; STAMP(2, 5); }
    } else {
      {
#pragma unroll 1
        for (int n = 0; __any_sync(~0u, stale8(f, tag) & 1); n++) {
#pragma unroll
          for (int p = 0; p < 8; p++) ld_stale4(f[p], psrc + p * 2176, tag);
          if (n > SPIN_LIMIT) __trap();
        }
        float s0 = 0.f, s1 = 0.f, s2 = 0.f, s3 = 0.f;
#pragma unroll
        for (int p = 0; p < 8; p++) { s0 += __uint_as_float(f[p].x); s1 += __uint_as_float(f[p].y); s2 += __uint_as_float(f[p].z); s3 += __uint_as_float(f[p].w); }
        if (hw < 2 || lane < 2) st_tag4(P.kv + hp * 2176 + (4 * pi), s0, s1, s2, s3, tag);
      }
      const uint32_t cs2 = clock();
      if (lane == 0 && hw == 0) STAMP(3, 8);
      H2_READY();
      if (hw == 2) {
        unsigned* cnt = OCNT(2 * mb + lane, 0);
#pragma unroll 1
        for (int hh = 0; hh < 2; hh++) {
          mbar_wait(BAR(hh ? B_ODONE1 : B_ODONE), 0);
          if (lane < 2) asm volatile("red.release.gpu.global.add.u32 [%0], 1;" ::"l"(cnt) : "memory");
          if (OLOC && hh == 0 && lane < 2) mbar_arrive_cl(BAR(B_OLOC), lane);
          cnt += 32;
          if (lane == 0) STAMP(3, hh ? 6 : 7);
        }
        poll_ge(OCNT(rb, 1), 16 * (epoch + 1));
        asm volatile("fence.proxy.async.global;" ::: "memory");
        if (lane == 0) { mbar_arrive(BAR(B_O1RDY)); STAMP(2, 4); }
        __syncwarp();
      } else {
        const int t = tid - 288;
        const float* src = P.kv + hp * 2176 + 4 * (t + 32 * hw);
        const float* zsrc = P.kv + hp * 2176 + (2048 + (t & 48) + 2 * (lane & 6));
        mbar_wait(BAR(B_PKFREE), 0);
        while (__any_sync(~0u, (uint32_t)clock() - cs2 < PD2)) __nanosleep(20);
        uint4 zp = ld_rlx4(zsrc);
#pragma unroll
        for (int p = 0; p < 8; p++) f[p] = ld_rlx4(src + 4 * ((p & 3) * 128 + (p >> 2) * 32));
        if (!opaque_true()) __trap();
#pragma unroll 1
        for (int n = 0; __any_sync(~0u, (stale8(f, tag) | (zp.x ^ tag)) & 1); n++) {
          ld_stale4(zp, zsrc, tag);
#pragma unroll
          for (int p = 0; p < 8; p++) ld_stale4(f[p], src + 4 * ((p & 3) * 128 + (p >> 2) * 32), tag);
          if (n > SPIN_LIMIT) __trap();
        }
#define PK2U(a, b) pk2(__uint_as_float(a), __uint_as_float(b))
        const uint32_t zf = (lane & 1) ? ((lane & 8) ? zp.w : zp.z) : ((lane & 8) ? zp.y : zp.x);
        const uint32_t zz = PK2U(zf, zf);
        *(uint4*)(smem + OFF_KVB + hw * 2560 + 2048 + lane * 16) = make_uint4(zz, zz, zz, zz);
#pragma unroll
        for (int hh = 0; hh < 2; hh++) {
          const uint4* ff = &f[4 * hh];
          uint8_t* dst = smem + OFF_KVB + hw * 2560 + q * 512 + (16 * hh + g) * 16;
          *(uint4*)dst = make_uint4(PK2U(ff[0].x, ff[0].y), PK2U(ff[1].x, ff[1].y), PK2U(ff[2].x, ff[2].y), PK2U(ff[3].x, ff[3].y));
          *(uint4*)(dst + 128) = make_uint4(PK2U(ff[0].z, ff[0].w), PK2U(ff[1].z, ff[1].w), PK2U(ff[2].z, ff[2].w), PK2U(ff[3].z, ff[3].w));
        }
        fence_async();
        __syncwarp();
        if (lane == 0) { mbar_arrive(BAR(hw ? B_KV1 : B_KV)); if (hw == 0) STAMP(3, 9); }
      }
#define QBUF(ci) (sb + 2048 * (ci) + ((ci) < 6 ? OFF_STG : (ci) < 10 ? OFF_SPARE - 6 * 2048 : OFF_F2F - 10 * 2048))
      mbar_wait(BAR(B_Y), 0);
      if (elect_one()) {
        mbar_expect(sbar + 8, 4096);
#pragma unroll 1
        for (int ci = hw ? hw + 9 : 12; ci < 16; ci += 3) tma3d(QBUF(ci), &P.tmQ, 16 * cl, 64 * rank + 32, 2 * (ci & 7), sbar + 8);
      }
      mbar_wait(BAR(B_Q), 0);
      mbar_wait(sbar, hw == 0);
      {
        const uint2 f0 = *(const uint2*)(smem + OFF_SCALE + 8 * q), f1 = *(const uint2*)(smem + OFF_SCALE + 32 + 8 * q);
        const uint32_t sc0 = __byte_perm(f0.x, f0.y, 0x7632), sc1 = __byte_perm(f1.x, f1.y, 0x7632);
        const uint32_t yl = sb + OFF_XT + (lane & 7) * XT_STRIDE + (lane >> 3) * 16;
#pragma unroll 1
        for (int ci = hw; ci < 16; ci += 3) {
          const uint32_t qb = QBUF(ci);
          if (ci >= 10) mbar_wait(sbar + 8, 1);
          uint32_t yy[4][4], qq[4][4];
          const uint32_t qa = qb + lane * 32 + ((lane & 4) << 2);
#pragma unroll
          for (int u = 0; u < 4; u++) {
            ldsm4t(yy[u], yl + (u & 1) * 2048 + (2 * ci + (u >> 1)) * 64);
            ldsm4(qq[u], (qa ^ ((u & 1) * 16)) + (u >> 1) * 1024);
          }
          if (!opaque_true()) __trap();
#pragma unroll
          for (int u = 0; u < 4; u++) {
#pragma unroll
            for (int m = 0; m < 4; m++) {
              const float2 f = __half22float2(*(const __half2*)&yy[u][m]);
              qq[u][m] = hmul(qq[u][m], hmul(pk2(f.x, f.y), (u & 1) ? sc1 : sc0));
            }
            stsm4((qa ^ ((u & 1) * 16)) + (u >> 1) * 1024, qq[u][0], qq[u][1], qq[u][2], qq[u][3]);
          }
          fence_async();
          __syncwarp();
          if (elect_one()) tma3d_st(&P.tmOA, qb, 16 * cl, 64 * rank + 32 * (ci >> 3), 2 * (ci & 7));
        }
        asm volatile("cp.async.bulk.commit_group;\ncp.async.bulk.wait_group.read 0;" ::: "memory");
      }
      if (lane == 0) STAMP(3, 10 + hw);
    }
    }
  }
}

typedef CUresult (*EncodeFn)(CUtensorMap*, CUtensorMapDataType, cuuint32_t, void*, const cuuint64_t*, const cuuint64_t*,
                             const cuuint32_t*, const cuuint32_t*, CUtensorMapInterleave, CUtensorMapSwizzle,
                             CUtensorMapL2promotion, CUtensorMapFloatOOBfill);

static void enc(EncodeFn fn, CUtensorMap* m, const void* p, int rank, const cuuint64_t* dims, const cuuint64_t* strides,
                const cuuint32_t* box, CUtensorMapSwizzle swz, CUtensorMapL2promotion promo) {
  cuuint32_t es[4] = {1, 1, 1, 1};
  fn(m, CU_TENSOR_MAP_DATA_TYPE_BFLOAT16, rank, (void*)p, dims, strides, box, es, CU_TENSOR_MAP_INTERLEAVE_NONE, swz, promo,
     CU_TENSOR_MAP_FLOAT_OOB_FILL_NONE);
}

extern "C" void kernel_launch(void* const* d_in, const int* in_sizes, int n_in, void* d_out, int out_size) {
  void* fp = nullptr;
  cudaDriverEntryPointQueryResult qr;
  cudaGetDriverEntryPoint("cuTensorMapEncodeTiled", &fp, cudaEnableDefault, &qr);
  EncodeFn fn = (EncodeFn)fp;
  Params P;
  P.shift_k = (const __nv_bfloat16*)d_in[3]; P.h = (const __nv_bfloat16*)d_in[4]; P.D = (const __nv_bfloat16*)d_in[5];
  P.q = (const __nv_bfloat16*)d_in[0];
  cudaGetSymbolAddress((void**)&P.part, g_part); cudaGetSymbolAddress((void**)&P.kv, g_kv); cudaGetSymbolAddress((void**)&P.o, g_o);
  cudaGetSymbolAddress((void**)&P.thr, c_thr); cudaGetSymbolAddress((void**)&P.img, c_img);
  P.x = (const __nv_bfloat16*)d_in[6]; P.w = (const __nv_bfloat16*)d_in[7]; P.wo = (const __nv_bfloat16*)d_in[8];
  const CUtensorMapSwizzle S128 = CU_TENSOR_MAP_SWIZZLE_128B, S32 = CU_TENSOR_MAP_SWIZZLE_32B;
  const CUtensorMapL2promotion P0 = CU_TENSOR_MAP_L2_PROMOTION_NONE, P128 = CU_TENSOR_MAP_L2_PROMOTION_L2_128B;
  { cuuint64_t d[2] = {1024, 2048}, s[1] = {2048}; cuuint32_t b[2] = {64, 128}; enc(fn, &P.tmX, d_in[6], 2, d, s, b, S128, P128); }
  { cuuint64_t d[2] = {1024, 2048}, s[1] = {2048}; cuuint32_t b[2] = {64, 64}; enc(fn, &P.tmX0, d_in[6], 2, d, s, b, S128, P128); }
  { cuuint64_t d[3] = {1024, 1024, 3}, s[2] = {6144, 2048}; cuuint32_t b[3] = {64, 64, 3}; enc(fn, &P.tmW, d_in[7], 3, d, s, b, S128, P128); }
  { cuuint64_t d[4] = {64, 64, 16, 16}, s[3] = {2048, 131072, 128}; cuuint32_t b[4] = {64, 32, 2, 2}; enc(fn, &P.tmWo, d_in[8], 4, d, s, b, S128, P128); }
  { cuuint64_t d[4] = {64, 64, 16, 16}, s[3] = {2048, 131072, 128}; cuuint32_t b[4] = {64, 32, 2, 1}; enc(fn, &P.tmWo1, d_in[8], 4, d, s, b, S128, P128); }
  { cuuint64_t d[2] = {1024, 2048}, s[1] = {2048}; cuuint32_t b[2] = {16, 72}; enc(fn, &P.tmK, d_in[1], 2, d, s, b, S32, P128); }
  { cuuint64_t d[2] = {1024, 2048}, s[1] = {2048}; cuuint32_t b[2] = {16, 64}; enc(fn, &P.tmV, d_in[2], 2, d, s, b, S32, P128); }
  { cuuint64_t d[3] = {1024, 128, 16}, s[2] = {32768, 2048}; cuuint32_t b[3] = {16, 32, 2}; enc(fn, &P.tmQ, d_in[0], 3, d, s, b, S32, P128); }
  { cuuint64_t d[3] = {1024, 128, 16}, s[2] = {65536, 4096}; cuuint32_t b[3] = {16, 32, 2}; enc(fn, &P.tmOA, d_out, 3, d, s, b, S32, P0); }
  { cuuint64_t d[2] = {2048, 2048}, s[1] = {4096}; cuuint32_t b[2] = {64, 16}; enc(fn, &P.tmOB, d_out, 2, d, s, b, S128, P0); }
  cudaFuncSetAttribute(fused_kernel, cudaFuncAttributeMaxDynamicSharedMemorySize, SMEM_TOTAL);
  fused_kernel<<<128, 384, SMEM_TOTAL>>>(P);
}
```

```cpp
#include <cuda_runtime.h>
#include <cuda_bf16.h>
#include <cuda_fp16.h>
#include <cuda.h>
#include <stdint.h>

template<int TA, int TB, int SA=1> __device__ __forceinline__ void wgmma_ss_n192(float (&d)[96], uint64_t da, uint64_t db, int scale_d) {
  asm volatile("{\n.reg .pred p;\nsetp.ne.b32 p, %98, 0;\n"
    "wgmma.mma_async.sync.aligned.m64n192k16.f32.bf16.bf16 {%0, %1, %2, %3, %4, %5, %6, %7, %8, %9, %10, %11, %12, %13, %14, %15, %16, %17, %18, %19, %20, %21, %22, %23, %24, %25, %26, %27, %28, %29, %30, %31, %32, %33, %34, %35, %36, %37, %38, %39, %40, %41, %42, %43, %44, %45, %46, %47, %48, %49, %50, %51, %52, %53, %54, %55, %56, %57, %58, %59, %60, %61, %62, %63, %64, %65, %66, %67, %68, %69, %70, %71, %72, %73, %74, %75, %76, %77, %78, %79, %80, %81, %82, %83, %84, %85, %86, %87, %88, %89, %90, %91, %92, %93, %94, %95}, %96, %97, p, %101, 1, %99, %100;\n}\n"
    : "+f"(d[0]), "+f"(d[1]), "+f"(d[2]), "+f"(d[3]), "+f"(d[4]), "+f"(d[5]), "+f"(d[6]), "+f"(d[7]), "+f"(d[8]), "+f"(d[9]), "+f"(d[10]), "+f"(d[11]), "+f"(d[12]), "+f"(d[13]), "+f"(d[14]), "+f"(d[15]), "+f"(d[16]), "+f"(d[17]), "+f"(d[18]), "+f"(d[19]), "+f"(d[20]), "+f"(d[21]), "+f"(d[22]), "+f"(d[23]), "+f"(d[24]), "+f"(d[25]), "+f"(d[26]), "+f"(d[27]), "+f"(d[28]), "+f"(d[29]), "+f"(d[30]), "+f"(d[31]), "+f"(d[32]), "+f"(d[33]), "+f"(d[34]), "+f"(d[35]), "+f"(d[36]), "+f"(d[37]), "+f"(d[38]), "+f"(d[39]), "+f"(d[40]), "+f"(d[41]), "+f"(d[42]), "+f"(d[43]), "+f"(d[44]), "+f"(d[45]), "+f"(d[46]), "+f"(d[47]), "+f"(d[48]), "+f"(d[49]), "+f"(d[50]), "+f"(d[51]), "+f"(d[52]), "+f"(d[53]), "+f"(d[54]), "+f"(d[55]), "+f"(d[56]), "+f"(d[57]), "+f"(d[58]), "+f"(d[59]), "+f"(d[60]), "+f"(d[61]), "+f"(d[62]), "+f"(d[63]), "+f"(d[64]), "+f"(d[65]), "+f"(d[66]), "+f"(d[67]), "+f"(d[68]), "+f"(d[69]), "+f"(d[70]), "+f"(d[71]), "+f"(d[72]), "+f"(d[73]), "+f"(d[74]), "+f"(d[75]), "+f"(d[76]), "+f"(d[77]), "+f"(d[78]), "+f"(d[79]), "+f"(d[80]), "+f"(d[81]), "+f"(d[82]), "+f"(d[83]), "+f"(d[84]), "+f"(d[85]), "+f"(d[86]), "+f"(d[87]), "+f"(d[88]), "+f"(d[89]), "+f"(d[90]), "+f"(d[91]), "+f"(d[92]), "+f"(d[93]), "+f"(d[94]), "+f"(d[95])
    : "l"(da), "l"(db), "r"(scale_d), "n"(TA), "n"(TB), "n"(SA));
}
template<int TA, int TB, int SA=1> __device__ __forceinline__ void wgmma_ss_n128(float (&d)[64], uint64_t da, uint64_t db, int scale_d) {
  asm volatile("{\n.reg .pred p;\nsetp.ne.b32 p, %66, 0;\n"
    "wgmma.mma_async.sync.aligned.m64n128k16.f32.bf16.bf16 {%0, %1, %2, %3, %4, %5, %6, %7, %8, %9, %10, %11, %12, %13, %14, %15, %16, %17, %18, %19, %20, %21, %22, %23, %24, %25, %26, %27, %28, %29, %30, %31, %32, %33, %34, %35, %36, %37, %38, %39, %40, %41, %42, %43, %44, %45, %46, %47, %48, %49, %50, %51, %52, %53, %54, %55, %56, %57, %58, %59, %60, %61, %62, %63}, %64, %65, p, %69, 1, %67, %68;\n}\n"
    : "+f"(d[0]), "+f"(d[1]), "+f"(d[2]), "+f"(d[3]), "+f"(d[4]), "+f"(d[5]), "+f"(d[6]), "+f"(d[7]), "+f"(d[8]), "+f"(d[9]), "+f"(d[10]), "+f"(d[11]), "+f"(d[12]), "+f"(d[13]), "+f"(d[14]), "+f"(d[15]), "+f"(d[16]), "+f"(d[17]), "+f"(d[18]), "+f"(d[19]), "+f"(d[20]), "+f"(d[21]), "+f"(d[22]), "+f"(d[23]), "+f"(d[24]), "+f"(d[25]), "+f"(d[26]), "+f"(d[27]), "+f"(d[28]), "+f"(d[29]), "+f"(d[30]), "+f"(d[31]), "+f"(d[32]), "+f"(d[33]), "+f"(d[34]), "+f"(d[35]), "+f"(d[36]), "+f"(d[37]), "+f"(d[38]), "+f"(d[39]), "+f"(d[40]), "+f"(d[41]), "+f"(d[42]), "+f"(d[43]), "+f"(d[44]), "+f"(d[45]), "+f"(d[46]), "+f"(d[47]), "+f"(d[48]), "+f"(d[49]), "+f"(d[50]), "+f"(d[51]), "+f"(d[52]), "+f"(d[53]), "+f"(d[54]), "+f"(d[55]), "+f"(d[56]), "+f"(d[57]), "+f"(d[58]), "+f"(d[59]), "+f"(d[60]), "+f"(d[61]), "+f"(d[62]), "+f"(d[63])
    : "l"(da), "l"(db), "r"(scale_d), "n"(TA), "n"(TB), "n"(SA));
}
template<int TA, int TB, int SA=1> __device__ __forceinline__ void wgmma_ss_n72(float (&d)[36], uint64_t da, uint64_t db, int scale_d) {
  asm volatile("{\n.reg .pred p;\nsetp.ne.b32 p, %38, 0;\n"
    "wgmma.mma_async.sync.aligned.m64n72k16.f32.bf16.bf16 {%0, %1, %2, %3, %4, %5, %6, %7, %8, %9, %10, %11, %12, %13, %14, %15, %16, %17, %18, %19, %20, %21, %22, %23, %24, %25, %26, %27, %28, %29, %30, %31, %32, %33, %34, %35}, %36, %37, p, %41, 1, %39, %40;\n}\n"
    : "+f"(d[0]), "+f"(d[1]), "+f"(d[2]), "+f"(d[3]), "+f"(d[4]), "+f"(d[5]), "+f"(d[6]), "+f"(d[7]), "+f"(d[8]), "+f"(d[9]), "+f"(d[10]), "+f"(d[11]), "+f"(d[12]), "+f"(d[13]), "+f"(d[14]), "+f"(d[15]), "+f"(d[16]), "+f"(d[17]), "+f"(d[18]), "+f"(d[19]), "+f"(d[20]), "+f"(d[21]), "+f"(d[22]), "+f"(d[23]), "+f"(d[24]), "+f"(d[25]), "+f"(d[26]), "+f"(d[27]), "+f"(d[28]), "+f"(d[29]), "+f"(d[30]), "+f"(d[31]), "+f"(d[32]), "+f"(d[33]), "+f"(d[34]), "+f"(d[35])
    : "l"(da), "l"(db), "r"(scale_d), "n"(TA), "n"(TB), "n"(SA));
}
template<int TB, int SA=1> __device__ __forceinline__ void wgmma_rs_n40(float (&d)[20], uint32_t a0, uint32_t a1, uint32_t a2, uint32_t a3, uint64_t db, int scale_d) {
  asm volatile("{\n.reg .pred p;\nsetp.ne.b32 p, %25, 0;\n"
    "wgmma.mma_async.sync.aligned.m64n40k16.f32.bf16.bf16 {%0, %1, %2, %3, %4, %5, %6, %7, %8, %9, %10, %11, %12, %13, %14, %15, %16, %17, %18, %19}, {%20, %21, %22, %23}, %24, p, %27, 1, %26;\n}\n"
    : "+f"(d[0]), "+f"(d[1]), "+f"(d[2]), "+f"(d[3]), "+f"(d[4]), "+f"(d[5]), "+f"(d[6]), "+f"(d[7]), "+f"(d[8]), "+f"(d[9]), "+f"(d[10]), "+f"(d[11]), "+f"(d[12]), "+f"(d[13]), "+f"(d[14]), "+f"(d[15]), "+f"(d[16]), "+f"(d[17]), "+f"(d[18]), "+f"(d[19])
    : "r"(a0), "r"(a1), "r"(a2), "r"(a3), "l"(db), "r"(scale_d), "n"(TB), "n"(SA));
}
template<int TB> __device__ __forceinline__ void wgmma_hrs_n64(uint32_t (&d)[16], uint32_t a0, uint32_t a1, uint32_t a2, uint32_t a3, uint64_t db, int scale_d) {
  asm volatile("{\n.reg .pred p;\nsetp.ne.b32 p, %21, 0;\n"
    "wgmma.mma_async.sync.aligned.m64n64k16.f16.f16.f16 {%0, %1, %2, %3, %4, %5, %6, %7, %8, %9, %10, %11, %12, %13, %14, %15}, {%16, %17, %18, %19}, %20, p, 1, 1, %22;\n}\n"
    : "+r"(d[0]), "+r"(d[1]), "+r"(d[2]), "+r"(d[3]), "+r"(d[4]), "+r"(d[5]), "+r"(d[6]), "+r"(d[7]), "+r"(d[8]), "+r"(d[9]), "+r"(d[10]), "+r"(d[11]), "+r"(d[12]), "+r"(d[13]), "+r"(d[14]), "+r"(d[15])
    : "r"(a0), "r"(a1), "r"(a2), "r"(a3), "l"(db), "r"(scale_d), "n"(TB));
}
template<int TB> __device__ __forceinline__ void wgmma_hrs_n32(uint32_t (&d)[8], uint32_t a0, uint32_t a1, uint32_t a2, uint32_t a3, uint64_t db, int scale_d) {
  asm volatile("{\n.reg .pred p;\nsetp.ne.b32 p, %13, 0;\n"
    "wgmma.mma_async.sync.aligned.m64n32k16.f16.f16.f16 {%0, %1, %2, %3, %4, %5, %6, %7}, {%8, %9, %10, %11}, %12, p, 1, 1, %14;\n}\n"
    : "+r"(d[0]), "+r"(d[1]), "+r"(d[2]), "+r"(d[3]), "+r"(d[4]), "+r"(d[5]), "+r"(d[6]), "+r"(d[7])
    : "r"(a0), "r"(a1), "r"(a2), "r"(a3), "l"(db), "r"(scale_d), "n"(TB));
}

__device__ __align__(128) const uint32_t c_thr[1536] = {
  0x33fb33ff,0xa49c9de4,0x33273352,0xaf2cae76,0x33e233f1,0xa96ca7bd,0x32c432f7,0xb045afdd,0x33b733cf,0xac3eaaf7,0x3250328c,0xb0eab099,
  0x3378339a,0xadbcacff,0x31cd3211,0xb182b137,0x33d033fb,0xaadea46a,0x299e2d17,0xb3e0b396,0x32fb337a,0xafd2adb1,0xa78b1f76,0xb3f2b3ff,
  0x318b3254,0xb1c5b0e5,0xae6bac32,0xb354b3b8,0x2f4230a3,0xb321b285,0xb133b040,0xb215b2c7,0x337c33f2,0xada5a759,0xb179afc8,0xb1d6b2fe,
  0x31463293,0xb204b08e,0xb394b2ba,0xad23b055,0x2b402f4e,0xb3cbb31e,0xb3e4b3f9,0x293ba533,0xac269c52,0xb3bab400,0xb258b357,0x30e02e5f,
  0x330133e5,0xafbda922,0xb3f3b3c9,0x2727ab59,0x2deb314a,0xb36fb200,0xb194b32f,0x31bc2f0a,0xacdb2084,0xb39fb3ff,0xa565aea4,0x33f93347,
  0xb2b6b0db,0xb05ab25c,0x30892c1a,0x329733bc,0x326033d4,0xb0d6aa94,0xb00ab29b,0x32e83084,0x20e82f64,0xb3feb318,0x2d8da597,0x338133f8,
  0xb1fcae48,0xb14fb35c,0x339031b8,0x2d3a3199,0xb3e6b3ae,0x2909ac7b,0x32d133f4,0xb030a6f5,0x319d33bf,0xb1b3ac02,0x2e3ca874,0x335e33ec,
  0xacc32b89,0xb3a3b3c6,0x33f83276,0x25c930b7,0xb3dcb1f8,0xaa01b154,0x30653335,0xb2b0aef4,0xb107b383,0x32392d81,0xafa6214d,0xb307b3fe,
  0x30bc33a5,0xb273acb7,0x33c5311b,0x2ba23229,0xb0cc94b6,0xb267b400,0x30153360,0xb2e1ae31,0xb385b3ab,0x2d76ac93,0xb166a691,0xb1e7b3f5,
  0x22deb06a,0x33fd32ac,0xb337b3da,0x2ee8aa19,0x2f853387,0xb310ad6a,0x322d33fe,0xb1162216,0xb2a9abd3,0xb06fb3c2,0xb07428a6,0xb2a5b3ea,
  0xb111b3e9,0x323128be,0xb30db3c3,0x2f90abba,0x31aa227a,0x31a633fd,0x2e25ad5e,0x33633389,0x2d6a3365,0xb387ae1a,0xa21631aa,0xb3feb1a6,
  0xb3c2af85,0xabd3b310,0xb3eab22d,0x28a6b116,0xa8beb2a9,0x33e9306f,0x2bbab074,0x33c332a5,0x33fd3111,0x227a3231,0x3389330d,0xad5e2f90,
  0x2a63333f,0xb3d7aec6,0xb2a2a1b1,0xb07ab3fe,0xb3f7b158,0x25fbb1f4,0xacb7b38b,0x33a52d52,0x2e0eb025,0x336832d8,0x340030bc,0x14b63273,
  0x323533c0,0xb10c2beb,0xac9330cc,0xb3abb267,0x23433316,0xb3fdaf6f,0xb38eb225,0x2d46b11f,0xb342b29e,0x2ebbb07f,0x31e3aa7c,0x316b33d6,
  0x3264a6c3,0x30d133f5,0x2c0233ac,0xb3bfac87,0x28f0336a,0xb3e7ae02,0xb3c6b19d,0x2b89b1b3,0xa59732e8,0xb3f8b00a,0xaccfb3ed,0x33a1285b,
  0xb1b8b381,0x3199ad8d,0x336c31df,0xadf73170,0x33f42d3a,0x26f53390,0xb30423a7,0xafb2b3fc,0xb05f3030,0xb2b3b2d1,0x29e8b27a,0x33dd30b2,
  0xab5932b6,0xb3c9b05a,0x30adb089,0x327e3297,0xaf0ab3f3,0x332fa727,0x240633b0,0xb3fcac6f,0x33473194,0xaea431bc,0xb174b359,0x31daae54,
  0xb3bca565,0xac1ab3f9,0x33ee2f59,0xa842331b,0xaddf3281,0xb371b0a8,0x34002b40,0x1c5233cb,0xa759b3ef,0x33f22829,0xb2fe2c26,0xafc8b3ba,
  0x308e337c,0xb2932da5,0x3055b179,0x32ba31d6,0xb31eb146,0x2f4eb204,0xa5333394,0xb3f9ad23,0xaff33249,0xb2f1b0f3,0x30e532fb,0xb2542fd2,
  0x2b28b373,0x33cc2dd4,0xb285b18b,0x30a3b1c5,0x246a33fa,0xb3fba500,0x33962f42,0xad173321,0xadb1b3d0,0x337aaade,0xb3ffa99e,0x1f76b3e0,
  0xb0ee320d,0xb24db13c,0xac4b3398,0xb3b5ad0b,0x304ab289,0x32c1309e,0x2985b3ce,0x33e12b0f,0xaf3732f4,0xb324afe8,0xa4ce33f0,0xb3faa7ef,
  0x2dc8b34f,0x33762e82,0x9de4b3ff,0x33ff1ead,0xb1c931cd,0xb186b182,0xb3762e82,0xadc8b34f,0x324db13c,0x30ee320d,0x33b5ad0b,0x2c4b3398,
  0xb2c1309e,0xb04ab289,0xb3e12b0f,0xa985b3ce,0x3324afe8,0x2f3732f4,0x33faa7ef,0x24ce33f0,0xb285318b,0xb0a3b1c5,0xb2c7ae6b,0x3040b354,
  0x3396af42,0x2d173321,0x31413133,0xb2093215,0xb3ff299e,0x9f76b3e0,0xae8db2bd,0x334cb050,0x33b8278b,0xac3233f2,0x281033b3,0xb3ef2c57,
  0xb31e3146,0xaf4eb204,0xa533b394,0x33f9ad23,0x3400ab40,0x9c5233cb,0xae5f33e4,0xb357a93b,0xb2feac26,0x2fc8b3ba,0x3245b258,0x30f830e0,
  0x30553179,0xb2ba31d6,0xb3df2e99,0xa9b6b34a,0xb39230fd,0xad2fb241,0x3200b301,0x314a2fbd,0x337f1b11,0xad993400,0xb3ff2deb,0xa084b36f,
  0xb005b129,0x32ebb21d,0x325c2cdb,0xb0db339f,0xa92233de,0xb3e529cf,0xab59b2b6,0x33c9b05a,0xb3dd30b2,0xa9e8b27a,0x33d4ab71,0xaa9433c8,
  0x32212c0e,0xb12433bd,0xaf64b0d6,0x3318b260,0x197fb345,0x3400aeaf,0xae4833fe,0xb35c20e8,0xb23d3332,0xb102aeff,0x33aeb14f,0x2c7b31fc,
  0xb3fe3065,0xa14db2b0,0x2ebb307f,0xb342329e,0x300f2fa6,0xb2e53307,0x30d1b3f5,0x326426c3,0x302ab400,0x32d517db,0xb3e72e02,0x28f0b36a,
  0xb3fd2f6f,0x2343b316,0x2d46311f,0xb38e3225,0xb3f53015,0x2691b2e1,0xaf9b33eb,0xb30a288d,0x2a193166,0xb3da31e7,0x33d7aec6,0xaa63333f,
  0x3313b337,0x2f7a2ee8,0xa5fbb1f4,0x33f7b158,0xb1a1a8d7,0x31afb3e8,0xb36832d8,0xae0eb025,0xb3c22f85,0x2bd3b310,0xb3ea322d,0xa8a6b116,
  0xa8be32a9,0xb3e9306f,0x2bba3074,0xb3c332a5,0x33fdb111,0xa27a3231,0x3389b30d,0x2d5e2f90,0xa216b1aa,0x33feb1a6,0xaed2ae25,0x333db363,
  0xb3652edd,0x2e1ab33a,0xb1aa227a,0x31a6b3fd,0xaf853387,0xb3102d6a,0xb22d33fe,0xb116a216,0x32a9abd3,0xb06f33c2,0x307428a6,0xb2a533ea,
  0x3111b3e9,0x3231a8be,0x330db3c3,0x2f902bba,0xb2e12e31,0x3015b360,0x288db1a1,0x33ebb1af,0xb1e733f5,0xb1662691,0xb33f2f9b,0x2ec6b30a,
  0x2ee82a19,0xb33733da,0xb15833d7,0xb1f42a63,0x33e8b313,0x28d72f7a,0x302525fb,0xb2d833f7,0xb2392d81,0x3107b383,0x3307b3fe,0x2fa6214d,
  0xb35e33ec,0xae3ca874,0x97dbb00f,0x3400b2e5,0xa5c930b7,0xb3f83276,0xb316302a,0x2f6fb2d5,0x32b0aef4,0xb0653335,0xb29e33fd,0xb07f2343,
  0xb1702ccf,0x31dfb3a1,0x3345b124,0xaeaf3221,0xb3fc336c,0xa3a7adf7,0x3332b400,0x2eff997f,0xb0b23304,0xb27a2fb2,0x2b71b102,0x33c8b23d,
  0x2c0e29e8,0xb3bd33dd,0xb0d62a94,0x3260b3d4,0xb0892c1a,0x3297b3bc,0x2aad2842,0xb3d333ee,0xb3b0327e,0x2c6fb0ad,0x3241b035,0xb0fd32ce,
  0xb35933fc,0xae542406,0x3400b392,0x1b112d2f,0xaf5931da,0xb31b3174,0x321db37f,0x3129ad99,0xaf152ac6,0x332cb3d2,0xb1463293,0xb204308e,
  0xb281312e,0x30a8b219,0xab402f4e,0xb3cb331e,0xb3ef3371,0x2829addf,0x2c269c52,0xb3ba3400,0xb37c33f2,0xada52759,0x3179afc8,0xb1d632fe,
  0xacf32953,0x339cb3e3,0xb3fa33cc,0x2500ab28,0xb0942f21,0x3290b32a,0xb3d033fb,0xaade246a,0xb249317d,0x30f3b1d2,0xb2fb337a,0xafd22db1,
  0xb37332f1,0x2dd4aff3,0xb18b3254,0xb1c530e5,0xa96c27bd,0x33e2b3f1,0xb0452fdd,0x32c4b2f7,0xac3e2af7,0x33b7b3cf,0xb0ea3099,0x3250b28c,
  0xadbc2cff,0x3378b39a,0xb1823137,0x31cdb211,0xaf2c2e76,0x3327b352,0xb20d31c9,0x313cb186,0x313c3186,0xb20db1c9,0x2d0b2dc8,0xb398b376,
  0x309e30ee,0xb289b24d,0x2b0f2c4b,0xb3ceb3b5,0x2fe8304a,0xb2f4b2c1,0x27ef2985,0xb3f0b3e1,0x2e822f37,0xb34fb324,0x1ead24ce,0xb3ffb3fa,
  0xb2bdb209,0xb050b141,0xb290b32a,0x30942f21,0xb3b3b34c,0xac57ae8d,0xb0f3b1d2,0x3249317d,0xb400b3ef,0x1d1ba810,0xadd4aff3,0x337332f1,
  0xb39cb3e3,0x2cf32953,0xa500ab28,0x33fa33cc,0xae99b0f8,0x334a3245,0x33ff33b2,0x201f2c63,0x2438a9b6,0x33fc33df,0x332c33d2,0xaf15aac6,
  0x303a2ce7,0x32cb339e,0x30a83219,0xb281b12e,0x32ee31c0,0x2ffe3190,0x28292ddf,0xb3efb371,0x33b0327e,0x2c6f30ad,0xb241b035,0xb0fdb2ce,
  0x335933fc,0xae54a406,0xb400b392,0x1b11ad2f,0x2f5931da,0xb31bb174,0xb21db37f,0x31292d99,0xaaad2842,0xb3d3b3ee,0xa9cfb005,0x33de32eb,
  0x285b305f,0xb3edb2b3,0x2c0ea9e8,0x33bd33dd,0xb170accf,0xb1dfb3a1,0x33453124,0x2eaf3221,0xb3fcb36c,0x23a7adf7,0x33323400,0xaeff997f,
  0xb0b2b304,0x327a2fb2,0x2b713102,0xb3c8b23d,0xb400b2e5,0x17dbb00f,0x2e023264,0xb36ab0d1,0xaf6fb2d5,0x3316302a,0xb11fa8f0,0xb225b3e7,
  0x307f2343,0x329e33fd,0xb3d6b38e,0x2a7cad46,0x33f53342,0xa6c32ebb,0xac87b1e3,0x33ac316b,0x28d7af7a,0x33e83313,0xb2d8b3f7,0x3025a5fb,
  0x33eb31af,0x288d31a1,0x2bebae0e,0x33c03368,0x2ec6330a,0xb33faf9b,0x33fe3235,0x21b1310c,0xb1f4aa63,0xb158b3d7,0x2d5232a2,0xb38bb07a,
  0x33a7333d,0xacab2ed2,0x33f63162,0x262d31eb,0xaa4b301a,0xb3d8b2de,0x2a32326b,0xb3d9b0c7,0xb3f6b26f,0x265fb0c1,0xb3a9b020,0xac9fb2db,
  0x0e48b15d,0x340031f0,0xae1ab33a,0x33652edd,0xaed22e25,0xb33db363,0xb1eb0e48,0xb162b400,0xb2deb3a7,0x301aacab,0xb0c7b3f6,0x326b262d,
  0x30c1aa4b,0x326f33d8,0x32db2a32,0x302033d9,0x31f033f6,0xb15d265f,0x2edd33a9,0xb33aac9f,0xb2acb385,0x306aad76,0x2a19b166,0x33da31e7,
  0x3229a2de,0x311b33fd,0x33133337,0xaf7a2ee8,0x2e3133c5,0xb360aba2,0xb1a128d7,0xb1afb3e8,0xb3f5b015,0xa691b2e1,0xaf9bb3eb,0x330a288d,
  0x3154acc3,0x31f833a3,0x2ef433f8,0xb335a5c9,0x2d8133dc,0xb383aa01,0xb3feb065,0x214db2b0,0xb3ecb107,0x2874b239,0x300fafa6,0x32e53307,
  0x30b7ae3c,0x3276335e,0x302a3400,0xb2d517db,0x312433bd,0xb2212c0e,0xb318b260,0x2f64b0d6,0xb400aeaf,0x997fb345,0x335c20e8,0x2e4833fe,
  0x3102aeff,0x323d3332,0xac7b31fc,0xb3aeb14f,0x2a9433c8,0xb3d4ab71,0xb084b3e6,0x329ba909,0xb2ce2aad,0xb035b3d3,0x33e529cf,0x292233de,
  0x2d2fb241,0x339230fd,0xb14a2fbd,0xb200b301,0x2d993400,0xb37f1b11,0x2084b36f,0x33ff2deb,0xb2ebb21d,0x3005b129,0x30db339f,0xb25c2cdb,
  0xae5fb3e4,0x3357a93b,0xb190303a,0xb1c0b2cb,0x32453258,0xb0f830e0,0x2c63b2ee,0x33b22ffe,0xb3dfae99,0x29b6b34a,0x2ac633ff,0xb3d2a01f,
  0x339ea438,0x2ce733fc,0xb12eb32c,0x3219af15,0x33b8a78b,0x2c3233f2,0x2810b3b3,0x33ef2c57,0xb2c72e6b,0xb040b354,0x29533400,0xb3e31d1b,
  0x3141b133,0x32093215,0xaf21b39c,0x332aacf3,0xae8d32bd,0xb34cb050,0x317d3290,0xb1d23094,0x27bd33fb,0xb3f1249c,0x2fdd3327,0xb2f72f2c,
  0xaaf7b3e2,0x33cfa96c,0xb099b2c4,0x328cb045,0x2cff33b7,0xb39a2c3e,0x31373250,0xb21130ea,0xae76b378,0x3352adbc,0xb1c9b1cd,0x3186b182,
  0xb3ff1ead,0x1de4b3ff,0xb352adbc,0x2e76b378,0x33f1249c,0xa7bd33fb,0x32f72f2c,0xafdd3327,0xb3cfa96c,0x2af7b3e2,0xb28cb045,0x3099b2c4,
  0x339a2c3e,0xacff33b7,0x321130ea,0xb1373250,0x2953b400,0x33e31d1b,0x33ccadd4,0x2b283373,0xaf21339c,0xb32aacf3,0xb3fb2500,0x246ab3fa,
  0x317db290,0x31d23094,0x337a2ade,0xadb133d0,0xb2f130f3,0xaff3b249,0xb254afd2,0x30e5b2fb,0x339e2438,0xace733fc,0xb12e332c,0xb219af15,
  0xb190b03a,0x31c0b2cb,0x3371b0a8,0x2ddf3281,0x2c6332ee,0xb3b22ffe,0xb3f22829,0x2759b3ef,0x2ac6b3ff,0x33d2a01f,0x32932da5,0xb08e337c,
  0xaf0a33f3,0xb32fa727,0x2406b3b0,0x33fcac6f,0x3347b194,0x2ea431bc,0xb1743359,0xb1daae54,0xb3bc2565,0x2c1ab3f9,0x33eeaf59,0x2842331b,
  0x30ad3089,0xb27e3297,0xb2ceaaad,0x3035b3d3,0xb29ba909,0x3084b3e6,0x305f3030,0xb2b332d1,0x259732e8,0xb3f8300a,0x2ccfb3ed,0x33a1a85b,
  0x31b8b381,0x31992d8d,0xb36c31df,0xadf7b170,0xb3f42d3a,0x26f5b390,0x330423a7,0xafb233fc,0x316bb3d6,0x31e32a7c,0xb3832a01,0x2d81b3dc,
  0xb3bf2c87,0x2c02b3ac,0x28743239,0xb3ec3107,0x2b8931b3,0xb3c6319d,0x3276b35e,0x30b72e3c,0x31f8b3a3,0x31542cc3,0xb33525c9,0x2ef4b3f8,
  0x310c2beb,0xb23533c0,0x33abb267,0x2c9330cc,0x307ab3fe,0x32a2a1b1,0xb06aad76,0x32acb385,0xb3a52d52,0x2cb7b38b,0xb11b33fd,0xb229a2de,
  0x94b63273,0xb40030bc,0x3360aba2,0xae3133c5,0xb2de33a7,0xb01aacab,0xb0c733f6,0xb26b262d,0x30c12a4b,0xb26f33d8,0x32dbaa32,0xb02033d9,
  0x31f0b3f6,0x315d265f,0x2eddb3a9,0x333aac9f,0xb1eb8e48,0x3162b400,0xb3872e1a,0x2d6ab365,0xae25ad5e,0x3363b389,0x8e48b15d,0x3400b1f0,
  0xb3a7333d,0xacabaed2,0xb3f63162,0x262db1eb,0x2a4b301a,0xb3d832de,0xaa32326b,0xb3d930c7,0x33f6b26f,0x265f30c1,0x33a9b020,0xac9f32db,
  0x33c0b368,0x2beb2e0e,0x30cc94b6,0xb2673400,0x21b1b10c,0x33feb235,0x3385b3ab,0x2d762c93,0xb38b307a,0x2d52b2a2,0xa2deb06a,0x33fdb2ac,
  0xb0bc33a5,0xb2732cb7,0xb3c5311b,0x2ba2b229,0x26c32ebb,0xb3f53342,0xb3ac316b,0x2c87b1e3,0x336ab0d1,0xae023264,0xb19d33bf,0xb1b32c02,
  0x3225b3e7,0x311fa8f0,0x2cc32b89,0xb3a333c6,0xaa7cad46,0x33d6b38e,0x33dcb1f8,0xaa013154,0xb3fe3318,0x20e8af64,0x3381b3f8,0x2d8d2597,
  0xb14f335c,0xb1fc2e48,0x2d3ab199,0x3390b1b8,0x29092c7b,0xb3e633ae,0xb03026f5,0x32d1b3f4,0x32e8b084,0xb00a329b,0xb3ed32b3,0x285bb05f,
  0x29cfb005,0x33deb2eb,0xb05a325c,0xb2b630db,0xafbd2922,0x3301b3e5,0x27272b59,0xb3f333c9,0xb36f3200,0x2debb14a,0x31bcaf0a,0xb194332f,
  0xb39f33ff,0xacdba084,0x33f9b347,0xa5652ea4,0x3394b2ba,0xad233055,0xa438a9b6,0x33fcb3df,0x33e4b3f9,0x293b2533,0xb03a2ce7,0x32cbb39e,
  0x3258b357,0x30e0ae5f,0xb2ee31c0,0x2ffeb190,0x2e99b0f8,0x334ab245,0xb3ff33b2,0x201fac63,0xaf4230a3,0xb3213285,0x3133b040,0xb21532c7,
  0xa99e2d17,0xb3e03396,0x32bdb209,0xb0503141,0x278b1f76,0xb3f233ff,0x33b3b34c,0xac572e8d,0x2e6bac32,0xb35433b8,0x3400b3ef,0x1d1b2810,
  0xb289324d,0x309eb0ee,0xb3ce33b5,0x2b0fac4b,0xb2f432c1,0x2fe8b04a,0xb3f033e1,0x27efa985,0xb34f3324,0x2e82af37,0xb3ff33fa,0x1eada4ce,
  0xb3983376,0x2d0badc8,0xb3fb33ff,0xa49c1de4,0x351c35f6,0xac93a617,0xb8a3b93c,0x308d2a16,0x32f43448,0xb160afa5,0xb6a4b7fe,0x353a3389,
  0x2fa53160,0xb448b2f4,0xb389b53a,0x37fe36a4,0x26172c93,0xb5f6b51c,0xaa16b08d,0x393c38a3,0x34c3358c,0xac47a5b2,0xb85fb8f3,0x304229b1,
  0x327e33fd,0xb106af26,0xb63cb785,0x34e7330f,0x2f263106,0xb3fdb27e,0xb30fb4e7,0x3785363c,0x25b22c47,0xb58cb4c3,0xa9b1b042,0x38f3385f,
  0x346a3523,0xabf6a54d,0xb81ab8a8,0x2fef294d,0x3209336b,0xb0acaea7,0xb5d4b70a,0x34933294,0x2ea730ac,0xb36bb209,0xb294b493,0x370a35d4,
  0x254d2bf6,0xb523b46a,0xa94dafef,0x38a8381a,0x341334bc,0xab5fa4e9,0xb7a6b85a,0x2f5928e8,0x319432da,0xb052ae28,0xb56ab68d,0x343e3219,
  0x2e283052,0xb2dab194,0xb219b43e,0x368d356a,0x24e92b5f,0xb4bcb413,0xa8e8af59,0x385a37a6,0x33783456,0xaac8a484,0xb715b80a,0x2ec32884,
  0x3120324a,0xaff2ada9,0xb4ffb60e,0x33d3319e,0x2da92ff2,0xb24ab120,0xb19eb3d3,0x360e34ff,0x24842ac8,0xb456b378,0xa884aec3,0x380a3715,
  0x32cd33e3,0xaa31a420,0xb682b76f,0x2e2d281f,0x30ac31bb,0xaf3fad2a,0xb493b58d,0x33283122,0x2d2a2f3f,0xb1bbb0ac,0xb122b328,0x358d3493,
  0x24202a31,0xb3e3b2cd,0xa81fae2d,0x376f3682,0x3223331c,0xa999a376,0xb5ebb6c6,0x2d972776,0x3039312d,0xae8dacac,0xb426b50b,0x327c30a6,
  0x2cac2e8d,0xb12db039,0xb0a6b27c,0x350b3426,0x23762999,0xb31cb223,0xa776ad97,0x36c635eb,0x317a3257,0xa902a2ad,0xb552b61a,0x2d0026ad,
  0x2f8c309f,0xaddcac2e,0xb371b487,0x31cf3029,0x2c2e2ddc,0xb09faf8c,0xb029b1cf,0x34873371,0x22ad2902,0xb257b17a,0xa6adad00,0x361a3552,
  0x30d23194,0xa86ba1e4,0xb4b7b56a,0x2c6a25e4,0x2ea73012,0xad2aab5f,0xb294b402,0x31222f59,0x2b5f2d2a,0xb012aea7,0xaf59b122,0x34023294,
  0x21e4286b,0xb194b0d2,0xa5e4ac6a,0x356a34b7,0x302c30d2,0xa7a9a11b,0xb41ab4b7,0x2ba7251b,0x2dc22f0c,0xac79aa63,0xb1b6b2f7,0x30742e5f,
  0x2a632c79,0xaf0cadc2,0xae5fb074,0x32f731b6,0x211b27a9,0xb0d2b02c,0xa51baba7,0x34b7341a,0x2f0c3012,0xa67ba052,0xb2f7b402,0x2a7a2452,
  0x2cde2df5,0xab91a967,0xb0d7b1e8,0x2f8b2d65,0x29672b91,0xadf5acde,0xad65af8b,0x31e830d7,0x2052267b,0xb012af0c,0xa452aa7a,0x340232f7,
  0x2dc22ea7,0xa54d9f12,0xb1b6b294,0x294d2311,0x2bf62cde,0xaa31a86b,0xafefb0d7,0x2e2d2c6a,0x286b2a31,0xacdeabf6,0xac6aae2d,0x30d72fef,
  0x1f12254d,0xaea7adc2,0xa311a94d,0x329431b6,0x2c792d2a,0xa4209d7f,0xb074b122,0x281f217f,0x2a312b91,0xa8d0a6e0,0xae2daf8b,0x2cce2ade,
  0x26e028d0,0xab91aa31,0xaadeacce,0x2f8b2e2d,0x1d7f2420,0xad2aac79,0xa17fa81f,0x31223074,0x2a632b5f,0xa1e49bdb,0xae5faf59,0x25e41fdb,
  0x286b2967,0xa6e0a4e9,0xac6aad65,0x2ade28e8,0x24e926e0,0xa967a86b,0xa8e8aade,0x2d652c6a,0x1bdb21e4,0xab5faa63,0x9fdba5e4,0x2f592e5f,
  0x27a9286b,0x9f1298b6,0xaba7ac6a,0x23111cb6,0x254d267b,0xa420a1e4,0xa94daa7a,0x281f25e4,0x21e42420,0xa67ba54d,0xa5e4a81f,0x2a7a294d,
  0x18b61f12,0xa86ba7a9,0x9cb6a311,0x2c6a2ba7,0x211b21e4,0x98b69248,0xa51ba5e4,0x1cb61648,0x1f122052,0x9d7f9bdb,0xa311a452,0x217f1fdb,
  0x1bdb1d7f,0xa0529f12,0x9fdba17f,0x24522311,0x124818b6,0xa1e4a11b,0x96489cb6,0x25e4251b,0xa11ba1e4,0x18b61248,0x251b25e4,0x9cb69648,
  0x9f12a052,0x1d7f1bdb,0x23112452,0xa17f9fdb,0x9bdb9d7f,0x20521f12,0x1fdb217f,0xa452a311,0x924898b6,0x21e4211b,0x16481cb6,0xa5e4a51b,
  0xa7a9a86b,0x1f1218b6,0x2ba72c6a,0xa3119cb6,0xa54da67b,0x242021e4,0x294d2a7a,0xa81fa5e4,0xa1e4a420,0x267b254d,0x25e4281f,0xaa7aa94d,
  0x98b69f12,0x286b27a9,0x1cb62311,0xac6aaba7,0xaa63ab5f,0x21e41bdb,0x2e5f2f59,0xa5e49fdb,0xa86ba967,0x26e024e9,0x2c6a2d65,0xaadea8e8,
  0xa4e9a6e0,0x2967286b,0x28e82ade,0xad65ac6a,0x9bdba1e4,0x2b5f2a63,0x1fdb25e4,0xaf59ae5f,0xac79ad2a,0x24201d7f,0x30743122,0xa81fa17f,
  0xaa31ab91,0x28d026e0,0x2e2d2f8b,0xacceaade,0xa6e0a8d0,0x2b912a31,0x2ade2cce,0xaf8bae2d,0x9d7fa420,0x2d2a2c79,0x217f281f,0xb122b074,
  0xadc2aea7,0x254d1f12,0x31b63294,0xa94da311,0xabf6acde,0x2a31286b,0x2fef30d7,0xae2dac6a,0xa86baa31,0x2cde2bf6,0x2c6a2e2d,0xb0d7afef,
  0x9f12a54d,0x2ea72dc2,0x2311294d,0xb294b1b6,0xaf0cb012,0x267b2052,0x32f73402,0xaa7aa452,0xacdeadf5,0x2b912967,0x30d731e8,0xaf8bad65,
  0xa967ab91,0x2df52cde,0x2d652f8b,0xb1e8b0d7,0xa052a67b,0x30122f0c,0x24522a7a,0xb402b2f7,0xb02cb0d2,0x27a9211b,0x341a34b7,0xaba7a51b,
  0xadc2af0c,0x2c792a63,0x31b632f7,0xb074ae5f,0xaa63ac79,0x2f0c2dc2,0x2e5f3074,0xb2f7b1b6,0xa11ba7a9,0x30d2302c,0x251b2ba7,0xb4b7b41a,
  0xb0d2b194,0x286b21e4,0x34b7356a,0xac6aa5e4,0xaea7b012,0x2d2a2b5f,0x32943402,0xb122af59,0xab5fad2a,0x30122ea7,0x2f593122,0xb402b294,
  0xa1e4a86b,0x319430d2,0x25e42c6a,0xb56ab4b7,0xb17ab257,0x290222ad,0x3552361a,0xad00a6ad,0xaf8cb09f,0x2ddc2c2e,0x33713487,0xb1cfb029,
  0xac2eaddc,0x309f2f8c,0x302931cf,0xb487b371,0xa2ada902,0x3257317a,0x26ad2d00,0xb61ab552,0xb223b31c,0x29992376,0x35eb36c6,0xad97a776,
  0xb039b12d,0x2e8d2cac,0x3426350b,0xb27cb0a6,0xacacae8d,0x312d3039,0x30a6327c,0xb50bb426,0xa376a999,0x331c3223,0x27762d97,0xb6c6b5eb,
  0xb2cdb3e3,0x2a312420,0x3682376f,0xae2da81f,0xb0acb1bb,0x2f3f2d2a,0x3493358d,0xb328b122,0xad2aaf3f,0x31bb30ac,0x31223328,0xb58db493,
  0xa420aa31,0x33e332cd,0x281f2e2d,0xb76fb682,0xb378b456,0x2ac82484,0x3715380a,0xaec3a884,0xb120b24a,0x2ff22da9,0x34ff360e,0xb3d3b19e,
  0xada9aff2,0x324a3120,0x319e33d3,0xb60eb4ff,0xa484aac8,0x34563378,0x28842ec3,0xb80ab715,0xb413b4bc,0x2b5f24e9,0x37a6385a,0xaf59a8e8,
  0xb194b2da,0x30522e28,0x356a368d,0xb43eb219,0xae28b052,0x32da3194,0x3219343e,0xb68db56a,0xa4e9ab5f,0x34bc3413,0x28e82f59,0xb85ab7a6,
  0xb46ab523,0x2bf6254d,0x381a38a8,0xafefa94d,0xb209b36b,0x30ac2ea7,0x35d4370a,0xb493b294,0xaea7b0ac,0x336b3209,0x32943493,0xb70ab5d4,
  0xa54dabf6,0x3523346a,0x294d2fef,0xb8a8b81a,0xb4c3b58c,0x2c4725b2,0x385f38f3,0xb042a9b1,0xb27eb3fd,0x31062f26,0x363c3785,0xb4e7b30f,
  0xaf26b106,0x33fd327e,0x330f34e7,0xb785b63c,0xa5b2ac47,0x358c34c3,0x29b13042,0xb8f3b85f,0xb51cb5f6,0x2c932617,0x38a3393c,0xb08daa16,
  0xb2f4b448,0x31602fa5,0x36a437fe,0xb53ab389,0xafa5b160,0x344832f4,0x3389353a,0xb7feb6a4,0xa617ac93,0x35f6351c,0x2a16308d,0xb93cb8a3,
};
__device__ __align__(128) const uint32_t c_img[2560] = {
  0x326d31ed,0x333b32dd,0x33c33388,0x33fe33ea,0x33c331ed,0x31ed33c3,0xa8b22d64,0xb33bb0c4,0x33ea31ed,0xad64301d,0xb2ddb388,0x315fa8b2,
  0x32dd31ed,0xb3feabc6,0x326dad64,0xad64326d,0x30c431ed,0xaed7b2dd,0x2bc63388,0xa248b3ea,0x2bc631ed,0x315fb3c3,0xb3ea2d64,0x2ed730c4,
  0xa8b231ed,0x3388b01d,0x301db388,0xb1ed28b2,0xb01d31ed,0x22482bc6,0x30c4ad64,0x3388b26d,0x33ea33fe,0x338833c3,0x32dd333b,0x31ed326d,
  0xb2ddb3fe,0xa248b01d,0x326d2ed7,0x338833ea,0x30c433fe,0xb33babc6,0xabc6b33b,0x33fe30c4,0xabc6b3fe,0x31ed32dd,0xb3eaaed7,0x333ba8b2,
  0xa8b233fe,0x2d64b3c3,0xb01d333b,0x315fb26d,0x301db3fe,0xb3fe301d,0x30c42ed7,0x2d64b3ea,0xb26d33fe,0x2ed72bc6,0x33c3b33b,0xa248b0c4,
  0x33c3b3fe,0x315fb2dd,0x28b2aed7,0xaed728b2,0xb0c4b15f,0xaed7b01d,0xabc6ad64,0xa248a8b2,0xabc6b15f,0x315f2bc6,0x33ea3388,0x2ed7326d,
  0x28b2b15f,0x338832dd,0xb01d2d64,0xb1edb3ea,0x301db15f,0x224833c3,0xb0c4b388,0x338830c4,0x326db15f,0xb33b301d,0x33c3ad64,0xb3fe28b2,
  0x33c3b15f,0xb1edabc6,0xa8b23388,0x333bb26d,0x33eab15f,0x2d64b2dd,0xb2dd2d64,0xb15f33ea,0x32ddb15f,0x33feb3c3,0x326db388,0x2d64b0c4,
  0x28b22248,0x2d642bc6,0x301d2ed7,0x315f30c4,0xb01da248,0xb3feb2dd,0xb0c4b33b,0x2d64a8b2,0x326d2248,0x2ed733c3,0xb3c3aed7,0xa248b26d,
  0xb3c3a248,0x315fb01d,0xa8b2333b,0xaed7b3ea,0x33ea2248,0xb388abc6,0x32dd2ed7,0xb1edb0c4,0xb2dda248,0x224832dd,0x326db33b,0xb38828b2,
  0x30c42248,0x333bb3c3,0xabc6aed7,0xb3fe326d,0xabc6a248,0xb1ed301d,0xb3ea333b,0xb33b33ea,0xb26d31ed,0xb33b32dd,0xb3c33388,0xb3fe33ea,
  0xb3c331ed,0xb1ed33c3,0x28b22d64,0x333bb0c4,0xb3ea31ed,0x2d64301d,0x32ddb388,0xb15fa8b2,0xb2dd31ed,0x33feabc6,0xb26dad64,0x2d64326d,
  0xb0c431ed,0x2ed7b2dd,0xabc63388,0x2248b3ea,0xabc631ed,0xb15fb3c3,0x33ea2d64,0xaed730c4,0x28b231ed,0xb388b01d,0xb01db388,0x31ed28b2,
  0x301d31ed,0xa2482bc6,0xb0c4ad64,0xb388b26d,0xb3ea33fe,0xb38833c3,0xb2dd333b,0xb1ed326d,0x32ddb3fe,0x2248b01d,0xb26d2ed7,0xb38833ea,
  0xb0c433fe,0x333babc6,0x2bc6b33b,0xb3fe30c4,0x2bc6b3fe,0xb1ed32dd,0x33eaaed7,0xb33ba8b2,0x28b233fe,0xad64b3c3,0x301d333b,0xb15fb26d,
  0xb01db3fe,0x33fe301d,0xb0c42ed7,0xad64b3ea,0x326d33fe,0xaed72bc6,0xb3c3b33b,0x2248b0c4,0xb3c3b3fe,0xb15fb2dd,0xa8b2aed7,0x2ed728b2,
  0x30c4b15f,0x2ed7b01d,0x2bc6ad64,0x2248a8b2,0x2bc6b15f,0xb15f2bc6,0xb3ea3388,0xaed7326d,0xa8b2b15f,0xb38832dd,0x301d2d64,0x31edb3ea,
  0xb01db15f,0xa24833c3,0x30c4b388,0xb38830c4,0xb26db15f,0x333b301d,0xb3c3ad64,0x33fe28b2,0xb3c3b15f,0x31edabc6,0x28b23388,0xb33bb26d,
  0xb3eab15f,0xad64b2dd,0x32dd2d64,0x315f33ea,0xb2ddb15f,0xb3feb3c3,0xb26db388,0xad64b0c4,0xa8b22248,0xad642bc6,0xb01d2ed7,0xb15f30c4,
  0x301da248,0x33feb2dd,0x30c4b33b,0xad64a8b2,0xb26d2248,0xaed733c3,0x33c3aed7,0x2248b26d,0x33c3a248,0xb15fb01d,0x28b2333b,0x2ed7b3ea,
  0xb3ea2248,0x3388abc6,0xb2dd2ed7,0x31edb0c4,0x32dda248,0xa24832dd,0xb26db33b,0x338828b2,0xb0c42248,0xb33bb3c3,0x2bc6aed7,0x33fe326d,
  0x2bc6a248,0x31ed301d,0x33ea333b,0x333b33ea,0x30c4315f,0x2ed7301d,0x2bc62d64,0x224828b2,0x2bc6315f,0xb15fabc6,0xb3eab388,0xaed7b26d,
  0xa8b2315f,0xb388b2dd,0x301dad64,0x31ed33ea,0xb01d315f,0xa248b3c3,0x30c43388,0xb388b0c4,0xb26d315f,0x333bb01d,0xb3c32d64,0x33fea8b2,
  0xb3c3315f,0x31ed2bc6,0x28b2b388,0xb33b326d,0xb3ea315f,0xad6432dd,0x32ddad64,0x315fb3ea,0xb2dd315f,0xb3fe33c3,0xb26d3388,0xad6430c4,
  0xa8b2a248,0xad64abc6,0xb01daed7,0xb15fb0c4,0x301d2248,0x33fe32dd,0x30c4333b,0xad6428b2,0xb26da248,0xaed7b3c3,0x33c32ed7,0x2248326d,
  0x33c32248,0xb15f301d,0x28b2b33b,0x2ed733ea,0xb3eaa248,0x33882bc6,0xb2ddaed7,0x31ed30c4,0x32dd2248,0xa248b2dd,0xb26d333b,0x3388a8b2,
  0xb0c4a248,0xb33b33c3,0x2bc62ed7,0x33feb26d,0x2bc62248,0x31edb01d,0x33eab33b,0x333bb3ea,0x326d31ed,0x333b32dd,0x33c33388,0x33fe33ea,
  0x33c331ed,0x31ed33c3,0xa8b22d64,0xb33bb0c4,0x33ea31ed,0xad64301d,0xb2ddb388,0x315fa8b2,0x32dd31ed,0xb3feabc6,0x326dad64,0xad64326d,
  0x30c431ed,0xaed7b2dd,0x2bc63388,0xa248b3ea,0x2bc631ed,0x315fb3c3,0xb3ea2d64,0x2ed730c4,0xa8b231ed,0x3388b01d,0x301db388,0xb1ed28b2,
  0xb01d31ed,0x22482bc6,0x30c4ad64,0x3388b26d,0x33ea33fe,0x338833c3,0x32dd333b,0x31ed326d,0xb2ddb3fe,0xa248b01d,0x326d2ed7,0x338833ea,
  0x30c433fe,0xb33babc6,0xabc6b33b,0x33fe30c4,0xabc6b3fe,0x31ed32dd,0xb3eaaed7,0x333ba8b2,0xa8b233fe,0x2d64b3c3,0xb01d333b,0x315fb26d,
  0x301db3fe,0xb3fe301d,0x30c42ed7,0x2d64b3ea,0xb26d33fe,0x2ed72bc6,0x33c3b33b,0xa248b0c4,0x33c3b3fe,0x315fb2dd,0x28b2aed7,0xaed728b2,
  0xb0c4315f,0xaed7301d,0xabc62d64,0xa24828b2,0xabc6315f,0x315fabc6,0x33eab388,0x2ed7b26d,0x28b2315f,0x3388b2dd,0xb01dad64,0xb1ed33ea,
  0x301d315f,0x2248b3c3,0xb0c43388,0x3388b0c4,0x326d315f,0xb33bb01d,0x33c32d64,0xb3fea8b2,0x33c3315f,0xb1ed2bc6,0xa8b2b388,0x333b326d,
  0x33ea315f,0x2d6432dd,0xb2ddad64,0xb15fb3ea,0x32dd315f,0x33fe33c3,0x326d3388,0x2d6430c4,0x28b2a248,0x2d64abc6,0x301daed7,0x315fb0c4,
  0xb01d2248,0xb3fe32dd,0xb0c4333b,0x2d6428b2,0x326da248,0x2ed7b3c3,0xb3c32ed7,0xa248326d,0xb3c32248,0x315f301d,0xa8b2b33b,0xaed733ea,
  0x33eaa248,0xb3882bc6,0x32ddaed7,0xb1ed30c4,0xb2dd2248,0x2248b2dd,0x326d333b,0xb388a8b2,0x30c4a248,0x333b33c3,0xabc62ed7,0xb3feb26d,
  0xabc62248,0xb1edb01d,0xb3eab33b,0xb33bb3ea,0xb26d31ed,0xb33b32dd,0xb3c33388,0xb3fe33ea,0xb3c331ed,0xb1ed33c3,0x28b22d64,0x333bb0c4,
  0xb3ea31ed,0x2d64301d,0x32ddb388,0xb15fa8b2,0xb2dd31ed,0x33feabc6,0xb26dad64,0x2d64326d,0xb0c431ed,0x2ed7b2dd,0xabc63388,0x2248b3ea,
  0xabc631ed,0xb15fb3c3,0x33ea2d64,0xaed730c4,0x28b231ed,0xb388b01d,0xb01db388,0x31ed28b2,0x301d31ed,0xa2482bc6,0xb0c4ad64,0xb388b26d,
  0xb3ea33fe,0xb38833c3,0xb2dd333b,0xb1ed326d,0x32ddb3fe,0x2248b01d,0xb26d2ed7,0xb38833ea,0xb0c433fe,0x333babc6,0x2bc6b33b,0xb3fe30c4,
  0x2bc6b3fe,0xb1ed32dd,0x33eaaed7,0xb33ba8b2,0x28b233fe,0xad64b3c3,0x301d333b,0xb15fb26d,0xb01db3fe,0x33fe301d,0xb0c42ed7,0xad64b3ea,
  0x326d33fe,0xaed72bc6,0xb3c3b33b,0x2248b0c4,0xb3c3b3fe,0xb15fb2dd,0xa8b2aed7,0x2ed728b2,0x29ed29ed,0x29ed29ed,0x29ed29ed,0x29ed29ed,
  0x2bc32a6d,0x2add2bea,0x23c628c4,0xa81da0b2,0x2bc32add,0xa3c6281d,0xabc3aadd,0x23c6a81d,0x29ed2b3b,0xabfea564,0x295fa6d7,0x1a482b88,
  0x25642b88,0xa564ab88,0x25642b88,0xa564ab88,0xa0b22bc3,0x2a6daadd,0xabea23c6,0x28c4281d,0xa8c42bea,0x2a6da0b2,0x28c4abea,0xaa6d20b2,
  0xab3b2bfe,0xa564295f,0x26d79a48,0x2b88a9ed,0x29ed29ed,0x29ed29ed,0x29ed29ed,0x29ed29ed,0xabc3aa6d,0xaaddabea,0xa3c6a8c4,0x281d20b2,
  0x2bc32add,0xa3c6281d,0xabc3aadd,0x23c6a81d,0xa9edab3b,0x2bfe2564,0xa95f26d7,0x9a48ab88,0x25642b88,0xa564ab88,0x25642b88,0xa564ab88,
  0x20b2abc3,0xaa6d2add,0x2beaa3c6,0xa8c4a81d,0xa8c42bea,0x2a6da0b2,0x28c4abea,0xaa6d20b2,0x2b3babfe,0x2564a95f,0xa6d71a48,0xab8829ed,
  0x295f295f,0x295f295f,0x295f295f,0x295f295f,0x23c628c4,0xa81da0b2,0xabc3aa6d,0xaaddabea,0xa3c6281d,0xabc3aadd,0x23c6a81d,0x2bc32add,
  0xa95f26d7,0x9a48ab88,0x29ed2b3b,0xabfea564,0xab882564,0x2b88a564,0xab882564,0x2b88a564,0xabea23c6,0x28c4281d,0x20b2abc3,0xaa6d2add,
  0xaa6d20b2,0xa8c42bea,0x2a6da0b2,0x28c4abea,0xa6d71a48,0xab8829ed,0xab3b2bfe,0xa564295f,0x295f295f,0x295f295f,0x295f295f,0x295f295f,
  0xa3c6a8c4,0x281d20b2,0x2bc32a6d,0x2add2bea,0xa3c6281d,0xabc3aadd,0x23c6a81d,0x2bc32add,0x295fa6d7,0x1a482b88,0xa9edab3b,0x2bfe2564,
  0xab882564,0x2b88a564,0xab882564,0x2b88a564,0x2beaa3c6,0xa8c4a81d,0xa0b22bc3,0x2a6daadd,0xaa6d20b2,0xa8c42bea,0x2a6da0b2,0x28c4abea,
  0x26d79a48,0x2b88a9ed,0x2b3babfe,0x2564a95f,0xabfe2bfe,0xabfe2bfe,0xabfe2bfe,0xabfe2bfe,0xaadd2bea,0xa3c628c4,0x281da0b2,0x2bc3aa6d,
  0xa81d2bc3,0x2adda3c6,0x281dabc3,0xaadd23c6,0x9a482b88,0x29edab3b,0xabfe2564,0x295f26d7,0x26d72b3b,0xa6d7ab3b,0x26d72b3b,0xa6d7ab3b,
  0x2a6d2add,0xabeaa3c6,0x28c4a81d,0x20b22bc3,0x2bea2a6d,0xa0b228c4,0xabeaaa6d,0x20b2a8c4,0x2b8829ed,0x2b3b2bfe,0x2564295f,0xa6d79a48,
  0xabfe2bfe,0xabfe2bfe,0xabfe2bfe,0xabfe2bfe,0x2addabea,0x23c6a8c4,0xa81d20b2,0xabc32a6d,0xa81d2bc3,0x2adda3c6,0x281dabc3,0xaadd23c6,
  0x1a48ab88,0xa9ed2b3b,0x2bfea564,0xa95fa6d7,0x26d72b3b,0xa6d7ab3b,0x26d72b3b,0xa6d7ab3b,0xaa6daadd,0x2bea23c6,0xa8c4281d,0xa0b2abc3,
  0x2bea2a6d,0xa0b228c4,0xabeaaa6d,0x20b2a8c4,0xab88a9ed,0xab3babfe,0xa564a95f,0x26d71a48,0x1a489a48,0x1a489a48,0x1a489a48,0x1a489a48,
  0x281da0b2,0x2bc3aa6d,0x2addabea,0x23c6a8c4,0x2adda3c6,0x281dabc3,0xaadd23c6,0xa81d2bc3,0x2bfea564,0xa95fa6d7,0x9a482b88,0x29edab3b,
  0x2b3ba6d7,0xab3b26d7,0x2b3ba6d7,0xab3b26d7,0x28c4a81d,0x20b22bc3,0xaa6daadd,0x2bea23c6,0x20b2a8c4,0x2bea2a6d,0xa0b228c4,0xabeaaa6d,
  0xa564a95f,0x26d71a48,0x2b8829ed,0x2b3b2bfe,0x1a489a48,0x1a489a48,0x1a489a48,0x1a489a48,0xa81d20b2,0xabc32a6d,0xaadd2bea,0xa3c628c4,
  0x2adda3c6,0x281dabc3,0xaadd23c6,0xa81d2bc3,0xabfe2564,0x295f26d7,0x1a48ab88,0xa9ed2b3b,0x2b3ba6d7,0xab3b26d7,0x2b3ba6d7,0xab3b26d7,
  0xa8c4281d,0xa0b2abc3,0x2a6d2add,0xabeaa3c6,0x20b2a8c4,0x2bea2a6d,0xa0b228c4,0xabeaaa6d,0x2564295f,0xa6d79a48,0xab88a9ed,0xab3babfe,
  0xa95fa95f,0xa95fa95f,0xa95fa95f,0xa95fa95f,0xa3c6a8c4,0x281d20b2,0x2bc32a6d,0x2add2bea,0x23c6a81d,0x2bc32add,0xa3c6281d,0xabc3aadd,
  0x295fa6d7,0x1a482b88,0xa9edab3b,0x2bfe2564,0x2b88a564,0xab882564,0x2b88a564,0xab882564,0x2beaa3c6,0xa8c4a81d,0xa0b22bc3,0x2a6daadd,
  0x2a6da0b2,0x28c4abea,0xaa6d20b2,0xa8c42bea,0x26d79a48,0x2b88a9ed,0x2b3babfe,0x2564a95f,0xa95fa95f,0xa95fa95f,0xa95fa95f,0xa95fa95f,
  0x23c628c4,0xa81da0b2,0xabc3aa6d,0xaaddabea,0x23c6a81d,0x2bc32add,0xa3c6281d,0xabc3aadd,0xa95f26d7,0x9a48ab88,0x29ed2b3b,0xabfea564,
  0x2b88a564,0xab882564,0x2b88a564,0xab882564,0xabea23c6,0x28c4281d,0x20b2abc3,0xaa6d2add,0x2a6da0b2,0x28c4abea,0xaa6d20b2,0xa8c42bea,
  0xa6d71a48,0xab8829ed,0xab3b2bfe,0xa564295f,0x29ed29ed,0x29ed29ed,0x29ed29ed,0x29ed29ed,0x2bc32a6d,0x2add2bea,0x23c628c4,0xa81da0b2,
  0x2bc32add,0xa3c6281d,0xabc3aadd,0x23c6a81d,0x29ed2b3b,0xabfea564,0x295fa6d7,0x1a482b88,0x25642b88,0xa564ab88,0x25642b88,0xa564ab88,
  0xa0b22bc3,0x2a6daadd,0xabea23c6,0x28c4281d,0xa8c42bea,0x2a6da0b2,0x28c4abea,0xaa6d20b2,0xab3b2bfe,0xa564295f,0x26d79a48,0x2b88a9ed,
  0x29ed29ed,0x29ed29ed,0x29ed29ed,0x29ed29ed,0xabc3aa6d,0xaaddabea,0xa3c6a8c4,0x281d20b2,0x2bc32add,0xa3c6281d,0xabc3aadd,0x23c6a81d,
  0xa9edab3b,0x2bfe2564,0xa95f26d7,0x9a48ab88,0x25642b88,0xa564ab88,0x25642b88,0xa564ab88,0x20b2abc3,0xaa6d2add,0x2beaa3c6,0xa8c4a81d,
  0xa8c42bea,0x2a6da0b2,0x28c4abea,0xaa6d20b2,0x2b3babfe,0x2564a95f,0xa6d71a48,0xab8829ed,0x9a481a48,0x9a481a48,0x9a481a48,0x9a481a48,
  0xa81d20b2,0xabc32a6d,0xaadd2bea,0xa3c628c4,0xaadd23c6,0xa81d2bc3,0x2adda3c6,0x281dabc3,0xabfe2564,0x295f26d7,0x1a48ab88,0xa9ed2b3b,
  0xab3b26d7,0x2b3ba6d7,0xab3b26d7,0x2b3ba6d7,0xa8c4281d,0xa0b2abc3,0x2a6d2add,0xabeaa3c6,0xa0b228c4,0xabeaaa6d,0x20b2a8c4,0x2bea2a6d,
  0x2564295f,0xa6d79a48,0xab88a9ed,0xab3babfe,0x9a481a48,0x9a481a48,0x9a481a48,0x9a481a48,0x281da0b2,0x2bc3aa6d,0x2addabea,0x23c6a8c4,
  0xaadd23c6,0xa81d2bc3,0x2adda3c6,0x281dabc3,0x2bfea564,0xa95fa6d7,0x9a482b88,0x29edab3b,0xab3b26d7,0x2b3ba6d7,0xab3b26d7,0x2b3ba6d7,
  0x28c4a81d,0x20b22bc3,0xaa6daadd,0x2bea23c6,0xa0b228c4,0xabeaaa6d,0x20b2a8c4,0x2bea2a6d,0xa564a95f,0x26d71a48,0x2b8829ed,0x2b3b2bfe,
  0xabfe2bfe,0xabfe2bfe,0xabfe2bfe,0xabfe2bfe,0xaadd2bea,0xa3c628c4,0x281da0b2,0x2bc3aa6d,0xa81d2bc3,0x2adda3c6,0x281dabc3,0xaadd23c6,
  0x9a482b88,0x29edab3b,0xabfe2564,0x295f26d7,0x26d72b3b,0xa6d7ab3b,0x26d72b3b,0xa6d7ab3b,0x2a6d2add,0xabeaa3c6,0x28c4a81d,0x20b22bc3,
  0x2bea2a6d,0xa0b228c4,0xabeaaa6d,0x20b2a8c4,0x2b8829ed,0x2b3b2bfe,0x2564295f,0xa6d79a48,0xabfe2bfe,0xabfe2bfe,0xabfe2bfe,0xabfe2bfe,
  0x2addabea,0x23c6a8c4,0xa81d20b2,0xabc32a6d,0xa81d2bc3,0x2adda3c6,0x281dabc3,0xaadd23c6,0x1a48ab88,0xa9ed2b3b,0x2bfea564,0xa95fa6d7,
  0x26d72b3b,0xa6d7ab3b,0x26d72b3b,0xa6d7ab3b,0xaa6daadd,0x2bea23c6,0xa8c4281d,0xa0b2abc3,0x2bea2a6d,0xa0b228c4,0xabeaaa6d,0x20b2a8c4,
  0xab88a9ed,0xab3babfe,0xa564a95f,0x26d71a48,0x3bfb3bff,0x3be53bf2,0x3bbf3bd4,0x3b873ba5,0x3bd03bfb,0x3b013b7c,0x399d3a60,0x378538bc,
  0x35173b52,0xbbc9b7c8,0xb074ba9b,0x3bfe391b,0x319e3b27,0xbbf3b979,0x363cb80a,0x3a2d3bc5,0xba093986,0x3a7eb8f8,0xbae5385f,0x3b3db77a,
  0xbabd393c,0x3bb0b699,0xbc00305b,0x3ba730d7,0xbb2a35c8,0xb8353bb2,0x3a64b1e8,0x3962bbf7,0xba90350b,0xba413bff,0x3602340e,0x3bf6bad8,
  0xac6aa5e4,0xb122af59,0xb402b294,0xb56ab4b7,0xb2deac9c,0xb7bdb5a5,0xb9b3b8d6,0xbb10ba73,0xbb96b676,0xb359bafe,0x3bec3884,0x2a163a29,
  0xbbe0b72c,0x2f27b9d6,0x3b5e3ae8,0xb91633a2,0xb941b9c9,0x38ad3a45,0xb80fbab3,0x36d23b13,0xb850ba0d,0x346f3b4a,0x1fdbbbed,0xb4ab3be8,
  0x3721bb76,0xbace3463,0xb8d13bdd,0x39ebadfb,0x3894bb98,0xb8fd281f,0xbb6a3bbd,0x2e2d3825,0x3b3f3b65,0x3ae83b16,0x3a813ab6,0x3a0d3a49,
  0x3263356a,0xad972b43,0xb5dfb359,0xb8eeb7f3,0xa9b139aa,0xbbedba25,0x3340b889,0x3b983afb,0xbaa2aa16,0xb4cfbb8e,0x3c0038ad,0xb44b38e5,
  0xbb853625,0x3bbdb4c3,0xbbe432ad,0x3bfbaf8b,0xbaacb6d2,0x39243954,0xb65fbace,0x2fbd3bb8,0xb9661648,0xba603bf8,0x383a31cf,0x3b27bbb3,
  0x3219b9eb,0xbb1836f4,0xb9903be5,0x37dd3010,0xb6c6b61a,0xb80ab76f,0xb8a8b85a,0xb93cb8f3,0xbbd7bb87,0xbbf8bbfd,0xbb71bbc9,0xba4dbaf1,
  0xbbfeb9a6,0x305bb91f,0x3bcb3a97,0xb50b37d2,0xb87abbfe,0x3ba13546,0x24523a7e,0xbbb5ba54,0xb576bb63,0x340e3ba3,0xb13bbbd3,0x2c9c3bf2,
  0x386abb3d,0xba2139f8,0x3b57b835,0xbbf13432,0x39e7bc00,0xb8d6adc9,0xbacb3bde,0x372c3457,0x3bdab962,0x3764bb35,0xb9c03122,0xbaf73bef,
  0x398b39cd,0x38fd3946,0x386538b2,0x37853815,0xba85b9c9,0xbb92bb1e,0xbbfebbdd,0xbbc2bbf5,0xb66b3682,0xbb01bb94,0x387fb371,0x3a2d3beb,
  0xbac7bb76,0x3a00ad33,0x36bb3bd4,0xbbeab79b,0xbc0026ad,0x3bf32c38,0xbbd6b109,0x3ba733eb,0x3153bbff,0xb70a3b9e,0x396bba9b,0xbade390c,
  0xb5d4b5bc,0xbbb03b2c,0x32013830,0x3bf6ba67,0x3bccbb52,0x2c06b92e,0xbb83385f,0xb8c73bab,0xb9c5b982,0xba41ba04,0xbab0ba7a,0xbb10bae1,
  0xb8a3b986,0xb52fb74e,0xa94db1e8,0x33d32e91,0xbb54bb4f,0x37bdb523,0x3a9e3bc8,0xb916308d,0x3840b5c8,0x394a3bf9,0xbb42b294,0xb0a6bb0a,
  0x251bbbff,0xaf273bfc,0x327cbbe6,0xb4ab3bc0,0x3be325e4,0xbb2fb4e7,0x39e33884,0xb81aba35,0x3b73bb78,0xb46fb715,0xbbdc3ad1,0x2e2d38cc,
  0x33283676,0x3bfcba19,0x3581bab3,0xba6b3493,0x363136dd,0x34cf3581,0x32c6341a,0x2fbd3153,0xbae1bb65,0xb970ba39,0xb715b889,0xb16cb4f3,
  0xb9a12a7a,0xb924bbfe,0x3a933042,0x37dd3bcc,0x308db9aa,0x3b453b07,0xb94632ad,0xb845bbfa,0xbb68b55e,0x3b1836bb,0xbabab805,0x3a4d38a3,
  0x3bc0b625,0xbbfe2ec3,0x3b9431cf,0xba89b742,0x9cb6b95d,0xbbf8396b,0xb1b63a5c,0x3bb5b840,0x38cc9648,0x3b81bbac,0xac38b85a,0xbbce3933,
  0xbb60bb3a,0xbba1bb83,0xbbd2bbbc,0xbbf1bbe3,0x3815361a,0x39df3907,0x3b2c3a97,0x3be23b9c,0xb9afbbfd,0x3a21294d,0x388e3bee,0xbaf7b328,
  0x3beb39a6,0xb6af37a6,0xba04bbd3,0x3ac42d00,0x360ebb89,0xb7643b42,0x3855baeb,0xb8ee3a85,0x33eb3b63,0x28e8bbf5,0xb5233bde,0x389ebb21,
  0x3c00b9f0,0x2d97b9e3,0xbbdf38db,0xb44b3ac7,0xba673c00,0x358d3487,0x3bfcbab6,0x330fba15,0x3b7a3bf1,0x394a3a93,0x33893764,0xb3d39cb6,
  0x3afb3be2,0x35eb3946,0xb4c328e8,0xbaa9b8cc,0x27763af7,0xbb2fbaba,0x3a76ad97,0x30a63b60,0xaf8b3ac4,0xb994bb94,0x3bf8358d,0xb8743815,
  0xbb4c38ee,0x3bfcb1b6,0xbad5b4cf,0x381a39af,0xbbb3389e,0x3b592c38,0xb76fb970,0xb24b3beb,0xb9d2344b,0xbb923bd2,0xb0f03924,0x3a6bb60e,
  0xb8f3330f,0xbc003b2c,0xb91f3b45,0x323233eb,0xb5b1afbd,0xba00b88e,0xbbc6bb18,0xbbc2bc00,0xb7d2b16c,0xbb6fba04,0xbba3bbfe,0xb86fba67,
  0xbbffb7dd,0x370ab855,0x38b73bf8,0xbbeab631,0xbbf2b845,0x39bcb523,0x2dc93b81,0xbaa5bae1,0xb68dba4d,0xac063bdf,0x382abba1,0xbade39a1,
  0xb457ba89,0xb6543bfc,0x3b16b9df,0xbbd8308d,0x397dbbb5,0xb52fb2c6,0xbbe73a21,0xb8c73b68,0x3a49bbce,0x2311b715,0xba2536af,0xbbd93bc0,
  0xb958b785,0xbb81ba9e,0xbbefbbf3,0xba89bb73,0xbbf7bbc2,0xb9b8bb42,0xaf59b70a,0x384a3328,0xbb8bba2d,0x39dfb27c,0x34263bb0,0xbbceb98b,
  0xb4b7bbea,0x3b6c39e3,0xbafe2c06,0x3185ba85,0xaadebba7,0xb6af3bdc,0x3a58ba41,0xbbe2366b,0x3a29bade,0xbc003581,0x3a45352f,0xb2f7bac7,
  0x3b37bbf6,0x28e8b865,0xbaee37bd,0xbac43c00,0x3b13b8c7,0x3b5cbbfe,0x3463b94a,0xb8993153,0xb9f4bb10,0xb58db87f,0x3029af27,0x389e35d4,
  0x2dfbb3d3,0x399936bb,0x3bf23b2f,0x3ac13bcc,0x3552b916,0x39703bd6,0xbbbab46f,0x330fb9c5,0x3ba530a6,0xb5f7396b,0xb7c8bbfc,0x3be138a3,
  0x3bfdb4ab,0xbb45b201,0x38e038fd,0xb16cbb54,0x391b381a,0xa17fbb83,0xb8f83b92,0x3bcfb840,0x36e82e2d,0x3bfebab0,0x37febb01,0xb845251b,
  0xb77a3a6b,0x3648294d,0x3bb2ba00,0x3a8cbbe3,0xb742b93c,0x2311b340,0x37a6340e,0x3aa93966,0x3b963a4d,0x3b7f3c00,0x380f3a21,0xb0be3219,
  0x3933b50b,0x35eb3be4,0xbbf5b8d6,0x3874b6c6,0x39413bb5,0xbbffb65f,0x38d1b764,0x33ba3bd7,0x3b9c2c9c,0xb994b83a,0x34873ae8,0x324bbbfe,
  0xb7213bf1,0x3b47b990,0xbbbf2d97,0x38c1387a,0x2d00372c,0x3b59b8a8,0x3a39bbed,0xb232b576,0xbbfb3af7,0xb9743b71,0x307434cf,0x3adbb86a,
  0x3b213a0d,0x3c003bcb,0x3b073bbd,0x386f39e7,0x351738ee,0xb599a452,0xbae5b924,0xbbe9bbda,0x3a153b98,0xbb6fb13b,0x2ec3ba60,0x3aa53b3f,
  0xba09344b,0xa884bb57,0x3a643b18,0xbbc3b263,0xb4f33bfb,0x39bcbacb,0xbbac380a,0x3bd8a9b1,0xbb2aafbd,0x36a439c0,0x3402bbf8,0xba6f3aa2,
  0xbbfa3b27,0xb6543a81,0x3907b05b,0x3bd9bb85,0x2c6ab7dd,0xb9da35df,0xbbec3ba1,0xb8203aac,0x3bf53b87,0x3b6c3bec,0x392e3a7e,0x32f73721,
  0xb9e7b785,0xbbfcbb5e,0xba81bbb0,0xb43eb894,0x379b3bfe,0xbc00b80f,0x374eb835,0x38993bfb,0xbb3fba2d,0x3b329fdb,0xb3403a41,0xb8eabbd0,
  0xb90c3b3d,0x3b5cb8d1,0xbbf93122,0x3ac13517,0x29b1bba7,0xb94f3b6a,0x3be4b7bd,0xbaf4b19e,0xbbab3962,0xb9993bbf,0x34e73359,0x3be1ba09,
  0x3b85bbf6,0x353ab99d,0xb83a2f27,0xbbf03abd,0x2e91356a,0xb5f7b074,0xba19b8ad,0xbbcfbb2a,0xb966bb10,0xaba7b63c,0x38a8346f,0x3bb73a90,
  0xbb0aaa16,0xa17fbae5,0x3b1e3ace,0xba8c2c6a,0x36c6b916,0x36ff3c00,0xbbcbb8fd,0x3a50b2de,0xba35b6d2,0x36483a64,0x2d33bbe5,0xb84a3b96,
  0x3bfeb4ab,0xb9fcb602,0x313b3b01,0x37e8bbe0,0x3493b9eb,0xb9b83402,0xbb9e3bc9,0xb1853941,0x35762e2d,0x3b90b9b3,0x3acbbbf3,0x2fefb850,
  0x3a543bcf,0x2884374e,0xb9f8b648,0xbbe9bbab,0x398b3bb7,0xb4db3340,0xbbdcb9fc,0xb911bb85,0xb4323a8c,0xb6a4bbf9,0x3b3539b8,0xbbc3ae91,
  0xb66b3a50,0xad65bbe4,0x38653b90,0xbb0db966,0xbbef384a,0x39da34e7,0x2b43bb6c,0xba6f3b0a,0xbc0037e8,0x3759383a,0x387fbbfc,0xbbf636c6,
  0xb7f33185,0xbb7f3a19,0xbb8e3c00,0xb8203a35,0xb5d42fef,0xba1d38a8,0xbbd63b32,0xbba93bfe,0xb8e5b2f7,0xbbffbb1e,0xb954bb5c,0x30beb493,
  0xb9c5b43e,0xbb9fbbcb,0xb201b94f,0x3a313576,0xbbb8b899,0x3b47ad33,0xb6f43999,0xb3babbf5,0xbb54b8ea,0x3bf9313b,0xbab0353a,0x3790b9e7,
  0xb010bac1,0xb9743b9e,0x3bfdb5f7,0xb8c1b79b,0x251bbaf4,0xbb1b3acb,0x3a9e2ba7,0x2e5fbb3f,0x3af1bbe1,0x3599b92e,0xb546a17f,0xbadb390c,
  0x3b73bbf0,0x3929ba81,0x327cb6ff,0xb49f29b1,0xb825baa9,0x353aaec3,0x3b7c3994,0x3af43bfa,0x360eb0be,0x3bf43a64,0x388e3b47,0xb7372c6a,
  0x38bcb874,0x2ba73bac,0xb979bb59,0x3bf03742,0x3c0033ba,0xbb043402,0x3855b974,0xacce3b96,0x3bc5b24b,0xb6ffb907,0xb6993c00,0x3bb7b933,
  0x363138c1,0x3902bbec,0xbbdf3599,0x34ff3941,0x30d73232,0x39fcb7a6,0x3bffbb6f,0x3a50bb9c,0xb9a13adb,0xb47b380f,0x32c62884,0x3937b721,
  0x3ad8386f,0x3b903bf5,0x35a539bc,0xb7e8ad00,0x3b683be9,0x2ef538d1,0xba93b6a4,0xbb24bbfb,0x3a733aa5,0xbbfcb487,0x39d6b654,0xafef3b21,
  0x1cb63bc3,0xb7b2bbbf,0x3aba39da,0xbbfab517,0xb3a23bd8,0x3b32ba39,0xbb4a2311,0x343e3a15,0xbb603a6f,0x3a3d3074,0x31b6bb7f,0xbb9a3a09,
  0xbbe83bd9,0xb94f3b07,0xa81f35eb,0x38eab4f3,0xb9af3820,0xbbae3ae5,0xbbd23bff,0xba113b2a,0x319e389e,0xb929b426,0xbc00bb45,0xb911bb37,
  0xbbffbac1,0xb805bafe,0x382a217f,0x3bfd3b13,0xbabd330f,0x34dbba58,0x36023bfe,0xbb0db9f4,0xb68dbbe1,0x3a5c3a45,0xbbe7b648,0x3b89adfb,
  0xba90b16c,0x2d653aee,0x39b3bb81,0xbbf63552,0x397dbbcf,0xbbbc3463,0x338939b8,0x39f0bba5,0x32deb845,0xb7593029,0xbb5e39df,0xbba93bfd,
  0x3b7aba8c,0x3beebbf2,0x3a76bb6c,0x36ddb91b,0xbbe0ba89,0xba1dbbba,0x1fdbb6af,0x3a3136e8,0xa776b84a,0x3aeb37c8,0x3ad53c00,0xaa7a377a,
  0xb850bbce,0x3b9f38e0,0xbb6a28e8,0x3790b958,0x3b4cb185,0xb8db38f8,0x30f0bb5c,0x355e3bf7,0x3894bbe2,0xbbf937fe,0x399d358d,0x2e5fbb8b,
  0x39d232f7,0x341abbb2,0xbbc63999,0x395d34b7,0x3bd0bac4,0x3b1bbbef,0x363cb970,0xb49faade,0xb5b13899,0x30422f59,0x38b7b5f7,0x3b3aba29,
  0x3219b3d3,0x3b0438b7,0x3b713bfc,0x34ff397d,0x36e83aa9,0xb8b2adc9,0xbbefbb59,0xb5bcba49,0x3bd730a6,0xb902382a,0xa452bb92,0x39373b7a,
  0xb9583874,0x3371bb16,0x34263c00,0xb982bafb,0x387a381a,0x347bbbe7,0xbb573a00,0x3b242776,0xbb8b324b,0x31093a25,0x3a58bb6f,0xbb4f2f8b,
  0xb86a3a6b,0x2ef53389,0x39c0b70a,0x3bfabb4c,0xaadeb232,0xb83034c3,0xbaee39bc,0xbbff3bb3,0x3bda3bc2,0x37b23a76,0xb5df2c06,0xbb9ab9d2,
  0xbb37b86f,0xba7abbf8,0x3029b654,0x3b7838f3,0x32633bea,0xba3dbad5,0x3c00352f,0xba1135b1,0xb9f4baa5,0x3bc8376f,0xbbba2311,0x39cdb7d2,
  0xbaa23ade,0x3baeb0f0,0xb65fb94a,0xb7373bff,0x3552bbd8,0xbbe6391f,0x38e035eb,0x3682bbf2,0xbaac38c7,0xbbf43bc6,0xb9903b2f,0xacce368d,
  0x3bfdbbd9,0x3ad1bba3,0x37feb994,0x26adb457,0x38a33b9a,0xb8dba452,0xbb83bbae,0x2a7ab86a,0x37423b78,0xbab6b426,0xb907bbe6,0x39aa2ade,
  0xb8403a11,0x341abb57,0x294d3bf4,0xb55ebbda,0xb93339cd,0x3889ba58,0xb7a63ad1,0x3625bb37,0xbbe33737,0x304239c0,0x3b42bb04,0xb95db263,
  0xbb9c3682,0xb2ad3aee,0x3bf5b8b2,0x1648b9f4,0xb3282cce,0xb80535df,0xb9e33902,0xbb3a3aa2,0xad0026ad,0xb1cf3029,0xb4873371,0xb61a3552,
  0xba85b4ff,0xba5cbc00,0x3581b47b,0x3bfd3aac,0xbb21b5bc,0xb85abbba,0x3a393109,0x39a63bfd,0xbac7b937,0x3bbc365f,0xbbfeaef5,0x3b89b219,
  0xba15b982,0x3a9738e0,0xbb07b830,0x3b6336e8,0x3153bb24,0xbbee3990,0x36bb37b2,0x39f0bbd7,0x34f3bb4f,0xbbd337fe,0xaec33a7a,0x3c00b958,
  0x3bccbbfa,0x3aebbb71,0x396bba3d,0x36ddb87a,0x3bfabbff,0x3bdebbef,0x3bacbbc8,0x3b65bb8b,0x3bc03911,0x38303b6a,0xb946ad65,0xbb4fbbd0,
  0x3a353bfd,0xb85f30f0,0xbb1ebbbc,0x35c8b5b1,0x38cc3b0d,0xba7ab99d,0x3b943759,0xbbffb19e,0xb4933b89,0x31e8bbc6,0xad333bee,0xa5e4bbff,
  0xb8153bf6,0x3bc8b63c,0xac38ba1d,0xbb783abd,0xbbf539f0,0x329438b7,0x3b9ebaeb,0xb676b68d,0xbbeb3ba9,0xbbe63c00,0xbb2c3b9f,0xb9cd3a90,
  0xb79b36dd,0xb884382a,0xb92e38db,0xb9c9397d,0x33eb3a31,0xbad1b602,0xba04bbf9,0x3682b2de,0xb90c2a7a,0xbab3bbe7,0x374eb41a,0x3b763b7a,
  0xba673790,0x38b2b9b3,0xb5233b1b,0x26adbbe0,0xbbabb55e,0x3bdd3389,0xbbf9b042,0x3bff2776,0xbae12e5f,0xb3713b5e,0x3bfcb929,0xb5bcb850,
  0xae91b95d,0xbbd43a76,0x34e73805,0x3b52bb4c,0x308db49f,0xb1091fdb,0xb71534db,0xb9823894,0x3b0abb3a,0x3a9bbad5,0x3a19ba5c,0x3986b9d2,
  0x2f8bb7e8,0x3bde3979,0x376f3b32,0xb9aab0d7,0x3bb83b24,0xb1223855,0xbbfdba3d,0xaa16b9a1,0x3bb3afef,0xbab63699,0x391fb94f,0xb6253ad8,
  0x30103bfa,0xb359bbdf,0x35463bae,0xb6d2bb68,0x38f3343e,0x3889bbff,0xbba3353a,0x96483a73,0xbaf13b9a,0x38ad32c6,0x39f8bbf4,0xb9eb9cb6,
  0xb7d238ea,0xb2ad35a5,0x2dc92ba7,0x361ab3a2,0xba543a11,0xbace3a93,0xbb353b04,0xbb873b60,0x3bf23af4,0x31cf39d6,0xbb16b6ff,0xb9a6bbe8,
  0xb4323737,0xbbe5baba,0x2b43b902,0x3bfe39af,0x34573bf0,0xb85abb4a,0x3a2539fc,0xbb63b825,0xbbef2cce,0x3bc9b1b6,0xbb8e347b,0x3b3db60e,
  0xba493bb7,0x3a97a81f,0x34c3bb90,0xbc0038bc,0xb7f3b4ff,0xba7e3bd2,0x39542ef5,0x3962bc00,0xbafb3a50,0xbbd33b7c,0xbbf83bfc,0xbb653bc5,
  0x38e5b937,0x3835b88e,0x36f4b7b2,0x356ab631,0xbb13bbe9,0x31e8b6f4,0x3bf239da,0x36763af1,0x3be83911,0x340e3ab0,0xbb7cb759,0xb72cbb73,
  0x2dfbbbc3,0x32943bfd,0xb7c8bb7f,0x39c93a54,0x38253b0d,0xb8d6ba9e,0x39793a1d,0xba0db98b,0x3ba5ba6f,0xb884b546,0xb8f83bff,0x3b76b432,
  0xb8bc3bf6,0x3ae8b27c,0x3699bb9f,0xbb98366b,0x391bb820,0x3ab3b9f8,0x3bb2bb47,0x3bffbbef,0xbbc53ba9,0xbbed3bdc,0xbbff3bf9,0xbbfb3c00,
  0x377ab0be,0x3bdd3b35,0x2f593974,0xbb52b7f3,0x30d73a31,0xbbbdb865,0xb5a5bb1b,0x3b2735d4,0x3bf733ba,0xbbd42b43,0x3afeb599,0xb98638e5,
  0xbad83790,0x3a60b87f,0xb9d63929,0x393cb9c5,0x34b738c1,0x3a9bbb8e,0xba45a884,0xb5c83bb8,0xba732e5f,0xb80a3bd6,0x3b4ab4db,0x350bbb54,
  0xba293adb,0xb85f3954,0xb46336a4,0x25e43010,0x33a2b49f,0x305bb201,0x281fad65,0xac9c251b,0x3f803f80,0x3f803f80,0x3f803f80,0x3f803f80,
  0x3f803f80,0x3f803f80,0x3f803f80,0x3f803f80,0x3f803f80,0x3f803f80,0x3f803f80,0x3f803f80,0x3f803f80,0x3f803f80,0x3f803f80,0x3f803f80,
  0x3f803f80,0x3f803f80,0x3f803f80,0x3f803f80,0x3f803f80,0x3f803f80,0x3f803f80,0x3f803f80,0x3f803f80,0x3f803f80,0x3f803f80,0x3f803f80,
  0x3f803f80,0x3f803f80,0x3f803f80,0x3f803f80,0x3f803f80,0x3f803f80,0x3f803f80,0x3f803f80,0x3f803f80,0x3f803f80,0x3f803f80,0x3f803f80,
  0x3f803f80,0x3f803f80,0x3f803f80,0x3f803f80,0x3f803f80,0x3f803f80,0x3f803f80,0x3f803f80,0x3f803f80,0x3f803f80,0x3f803f80,0x3f803f80,
  0x3f803f80,0x3f803f80,0x3f803f80,0x3f803f80,0x3f803f80,0x3f803f80,0x3f803f80,0x3f803f80,0x3f803f80,0x3f803f80,0x3f803f80,0x3f803f80,
  0x3f803f80,0x3f803f80,0x3f803f80,0x3f803f80,0x3f803f80,0x3f803f80,0x3f803f80,0x3f803f80,0x3f803f80,0x3f803f80,0x3f803f80,0x3f803f80,
  0x3f803f80,0x3f803f80,0x3f803f80,0x3f803f80,0x3f803f80,0x3f803f80,0x3f803f80,0x3f803f80,0x3f803f80,0x3f803f80,0x3f803f80,0x3f803f80,
  0x3f803f80,0x3f803f80,0x3f803f80,0x3f803f80,0x3f803f80,0x3f803f80,0x3f803f80,0x3f803f80,0x3f803f80,0x3f803f80,0x3f803f80,0x3f803f80,
  0x3f803f80,0x3f803f80,0x3f803f80,0x3f803f80,0x3f803f80,0x3f803f80,0x3f803f80,0x3f803f80,0x3f803f80,0x3f803f80,0x3f803f80,0x3f803f80,
  0x3f803f80,0x3f803f80,0x3f803f80,0x3f803f80,0x3f803f80,0x3f803f80,0x3f803f80,0x3f803f80,0x3f803f80,0x3f803f80,0x3f803f80,0x3f803f80,
  0x3f803f80,0x3f803f80,0x3f803f80,0x3f803f80,0x3f803f80,0x3f803f80,0x3f803f80,0x3f803f80,0x3f803f80,0x3f803f80,0x3f803f80,0x3f803f80,
  0x3f803f80,0x3f803f80,0x3f803f80,0x3f803f80,0x3f803f80,0x3f803f80,0x3f803f80,0x3f803f80,0x3f803f80,0x3f803f80,0x3f803f80,0x3f803f80,
  0x3f803f80,0x3f803f80,0x3f803f80,0x3f803f80,0x3f803f80,0x3f803f80,0x3f803f80,0x3f803f80,0x3f803f80,0x3f803f80,0x3f803f80,0x3f803f80,
  0x3f803f80,0x3f803f80,0x3f803f80,0x3f803f80,0x3f803f80,0x3f803f80,0x3f803f80,0x3f803f80,0x3f803f80,0x3f803f80,0x3f803f80,0x3f803f80,
  0x3f803f80,0x3f803f80,0x3f803f80,0x3f803f80,0x3f803f80,0x3f803f80,0x3f803f80,0x3f803f80,0x3f803f80,0x3f803f80,0x3f803f80,0x3f803f80,
  0x3f803f80,0x3f803f80,0x3f803f80,0x3f803f80,0x3f803f80,0x3f803f80,0x3f803f80,0x3f803f80,0x3f803f80,0x3f803f80,0x3f803f80,0x3f803f80,
  0x3f803f80,0x3f803f80,0x3f803f80,0x3f803f80,0x3f803f80,0x3f803f80,0x3f803f80,0x3f803f80,0x3f803f80,0x3f803f80,0x3f803f80,0x3f803f80,
  0x3f803f80,0x3f803f80,0x3f803f80,0x3f803f80,0x3f803f80,0x3f803f80,0x3f803f80,0x3f803f80,0x3f803f80,0x3f803f80,0x3f803f80,0x3f803f80,
  0x3f803f80,0x3f803f80,0x3f803f80,0x3f803f80,0x3f803f80,0x3f803f80,0x3f803f80,0x3f803f80,0x3f803f80,0x3f803f80,0x3f803f80,0x3f803f80,
  0x3f803f80,0x3f803f80,0x3f803f80,0x3f803f80,0x3f803f80,0x3f803f80,0x3f803f80,0x3f803f80,0x3f803f80,0x3f803f80,0x3f803f80,0x3f803f80,
  0x3f803f80,0x3f803f80,0x3f803f80,0x3f803f80,0x3f803f80,0x3f803f80,0x3f803f80,0x3f803f80,0x3f803f80,0x3f803f80,0x3f803f80,0x3f803f80,
  0x3f803f80,0x3f803f80,0x3f803f80,0x3f803f80,0x3f803f80,0x3f803f80,0x3f803f80,0x3f803f80,0x3f803f80,0x3f803f80,0x3f803f80,0x3f803f80,
  0x3f803f80,0x3f803f80,0x3f803f80,0x3f803f80,0x3f803f80,0x3f803f80,0x3f803f80,0x3f803f80,0x3f803f80,0x3f803f80,0x3f803f80,0x3f803f80,
  0x3f803f80,0x3f803f80,0x3f803f80,0x3f803f80,0x3f803f80,0x3f803f80,0x3f803f80,0x3f803f80,0x3f803f80,0x3f803f80,0x3f803f80,0x3f803f80,
  0x3f803f80,0x3f803f80,0x3f803f80,0x3f803f80,0x3f803f80,0x3f803f80,0x3f803f80,0x3f803f80,0x3f803f80,0x3f803f80,0x3f803f80,0x3f803f80,
  0x3f803f80,0x3f803f80,0x3f803f80,0x3f803f80,0x3f803f80,0x3f803f80,0x3f803f80,0x3f803f80,0x3f803f80,0x3f803f80,0x3f803f80,0x3f803f80,
  0x3f803f80,0x3f803f80,0x3f803f80,0x3f803f80,0x3f803f80,0x3f803f80,0x3f803f80,0x3f803f80,0x3f803f80,0x3f803f80,0x3f803f80,0x3f803f80,
  0x3f803f80,0x3f803f80,0x3f803f80,0x3f803f80,0x3f803f80,0x3f803f80,0x3f803f80,0x3f803f80,0x3f803f80,0x3f803f80,0x3f803f80,0x3f803f80,
  0x3f803f80,0x3f803f80,0x3f803f80,0x3f803f80,0x3f803f80,0x3f803f80,0x3f803f80,0x3f803f80,0x3f803f80,0x3f803f80,0x3f803f80,0x3f803f80,
  0x3f803f80,0x3f803f80,0x3f803f80,0x3f803f80,0x3f803f80,0x3f803f80,0x3f803f80,0x3f803f80,0x3f803f80,0x3f803f80,0x3f803f80,0x3f803f80,
  0x3f803f80,0x3f803f80,0x3f803f80,0x3f803f80,0x3f803f80,0x3f803f80,0x3f803f80,0x3f803f80,0x3f803f80,0x3f803f80,0x3f803f80,0x3f803f80,
  0x3f803f80,0x3f803f80,0x3f803f80,0x3f803f80,0x3f803f80,0x3f803f80,0x3f803f80,0x3f803f80,0x3f803f80,0x3f803f80,0x3f803f80,0x3f803f80,
  0x3f803f80,0x3f803f80,0x3f803f80,0x3f803f80,0x3f803f80,0x3f803f80,0x3f803f80,0x3f803f80,0x3f803f80,0x3f803f80,0x3f803f80,0x3f803f80,
  0x3f803f80,0x3f803f80,0x3f803f80,0x3f803f80,0x3f803f80,0x3f803f80,0x3f803f80,0x3f803f80,0x3f803f80,0x3f803f80,0x3f803f80,0x3f803f80,
  0x3f803f80,0x3f803f80,0x3f803f80,0x3f803f80,0x3f803f80,0x3f803f80,0x3f803f80,0x3f803f80,0x3f803f80,0x3f803f80,0x3f803f80,0x3f803f80,
  0x3f803f80,0x3f803f80,0x3f803f80,0x3f803f80,0x3f803f80,0x3f803f80,0x3f803f80,0x3f803f80,0x3f803f80,0x3f803f80,0x3f803f80,0x3f803f80,
  0x3f803f80,0x3f803f80,0x3f803f80,0x3f803f80,0x3f803f80,0x3f803f80,0x3f803f80,0x3f803f80,0x3f803f80,0x3f803f80,0x3f803f80,0x3f803f80,
  0x3f803f80,0x3f803f80,0x3f803f80,0x3f803f80,0x3f803f80,0x3f803f80,0x3f803f80,0x3f803f80,0x3f803f80,0x3f803f80,0x3f803f80,0x3f803f80,
  0x3f803f80,0x3f803f80,0x3f803f80,0x3f803f80,0x3f803f80,0x3f803f80,0x3f803f80,0x3f803f80,0x3f803f80,0x3f803f80,0x3f803f80,0x3f803f80,
  0x3f803f80,0x3f803f80,0x3f803f80,0x3f803f80,0x3f803f80,0x3f803f80,0x3f803f80,0x3f803f80,0x3f803f80,0x3f803f80,0x3f803f80,0x3f803f80,
  0x3f803f80,0x3f803f80,0x3f803f80,0x3f803f80,0x3f803f80,0x3f803f80,0x3f803f80,0x3f803f80,0x3f803f80,0x3f803f80,0x3f803f80,0x3f803f80,
  0x3f803f80,0x3f803f80,0x3f803f80,0x3f803f80,0x3f803f80,0x3f803f80,0x3f803f80,0x3f803f80,0x3f803f80,0x3f803f80,0x3f803f80,0x3f803f80,
  0x3f803f80,0x3f803f80,0x3f803f80,0x3f803f80,
};

__device__ __align__(128) float    g_part[16][8][2176];
__device__ __align__(128) float    g_kv[16][2176];
constexpr int OBLK = 16 * 1024 + 32;
__device__ __align__(128) uint4    g_o[16 * OBLK];
#define GSTAMP(role, i) do {} while (0)
#define STAMP(role, i) do {} while (0)
#define PDUMP(role) do {} while (0)
#define PROF_SMEM 0

constexpr int STAGE_BYTES = 57344;
constexpr int OFF_H = 4 * 16384, OFF_VP = 9 * 16384, OFF_SPARE = 10 * 16384;
constexpr int OFF_XT = 172032, XT_STRIDE = 4112;
constexpr int OFF_BAR = 204928, OFF_EPOCH = OFF_BAR + 640, OFF_EX = OFF_BAR + 656, OFF_D = OFF_BAR + 672, OFF_SCALE = OFF_BAR + 704;
constexpr int OFF_F2F = 205824, OFF_F2I = 207872, OFF_F4 = 209920, OFF_ONES = 214016, OFF_KVB = 214016;
constexpr int OFF_STG = 219136, STG_STRIDE = 4352, SMEM_TOTAL = 232192 + PROF_SMEM;
enum { B_FULL1 = 0, B_EMPTY1 = 3, B_Q = 6, B_ODONE1 = 7, B_O1RDY = 8, B_H = 9, B_XRAW = 10, B_XT = 11, B_KV = 12, B_Y = 13,  B_AFREE = 15,
       B_STG = 18, B_ODONE = 24, B_XFREE = 25, B_FULL2 = 33, B_CONS2 = 49, B_SFREE = 14, B_KV1 = 61, B_OLOC = 60, B_PKRDY = 62, B_PKFREE = 64, B_H2 = 65, B_G1DONE = 66, B_COUNT = 67, B_FIRST = 67 };
constexpr uint64_t SLOT_A = 0x6859468594685948ull, SLOT_B = 0x7103271032710326ull;
constexpr int NPRE = 6, BEARLY = 3;
__host__ __device__ constexpr int bar_count(int i) {
  return i < B_EMPTY1 ? 1 : i < B_Q ? 4 : i == B_XT ? 4 : i == B_H ? 4 : (i == B_SFREE || i == B_G1DONE) ? 2 : i >= B_PKFREE ? 4 : i >= B_PKRDY ? 8 : i == B_Y ? 9
       : (i >= B_AFREE && i < B_STG) ? 16 : (i == B_ODONE || i == B_ODONE1) ? 8 : (i >= B_XFREE && i < B_FULL2) ? 4
       : i == B_KV1 ? 1 : i == B_OLOC ? 2 : i >= B_CONS2 ? 4 : (i >= B_FULL2 && i < B_FULL2 + NPRE) ? 2 : 1;
}
__host__ __device__ constexpr uint64_t bar_counts(int r) {
  uint64_t v = 0;
  for (int w = 0; w < 11; w++) v |= (uint64_t)(bar_count(1 + 11 * r + w) - 1) << (4 * w);
  return v;
}
constexpr uint32_t SW128 = 64 | (1u << 30);
constexpr int SPIN_LIMIT = 1 << 22;
#define OLOC 1
#define G2E 1
#define G2P 1
#define RC 200
#define PFD 3
#define PD1 700
#define PD2 450
#define QPF 6
#define BPACE 250
#define OCH 3
#define O1D 0
#define HOLD2 12
#define D1 100
#define TRICK 3
#define HSTART 1500
#define PACE 800

__device__ __forceinline__ uint32_t smem_u32(const void* p) { return (uint32_t)__cvta_generic_to_shared(p); }
__device__ __forceinline__ void wg_fence() { asm volatile("wgmma.fence.sync.aligned;" ::: "memory"); }
__device__ __forceinline__ void wg_commit() { asm volatile("wgmma.commit_group.sync.aligned;" ::: "memory"); }
template <int N> __device__ __forceinline__ void wg_wait() { asm volatile("wgmma.wait_group.sync.aligned %0;" ::"n"(N) : "memory"); }
template <int N> __device__ __forceinline__ void keep(float (&d)[N]) {
#pragma unroll
  for (int i = 0; i < N; i++) asm volatile("" : "+f"(d[i])::"memory");
}
__device__ __forceinline__ void mbar_init(uint32_t bar, int cnt) { asm volatile("mbarrier.init.shared::cta.b64 [%0], %1;" ::"r"(bar), "r"(cnt)); }
__device__ __forceinline__ void mbar_expect(uint32_t bar, int bytes) { asm volatile("mbarrier.arrive.expect_tx.shared::cta.b64 _, [%0], %1;" ::"r"(bar), "r"(bytes) : "memory"); }
__device__ __forceinline__ void mbar_arrive(uint32_t bar) { asm volatile("mbarrier.arrive.shared::cta.b64 _, [%0];" ::"r"(bar) : "memory"); }
__device__ __forceinline__ void mbar_arrive_cl(uint32_t bar, uint32_t cta) {
  asm volatile("{\n.reg .b32 r;\nmapa.shared::cluster.u32 r, %0, %1;\nmbarrier.arrive.shared::cluster.b64 _, [r];\n}\n" ::"r"(bar), "r"(cta) : "memory");
}
__device__ __forceinline__ void mbar_wait(uint32_t bar, uint32_t parity) {
  asm volatile("{\n.reg .pred p;\n.reg .u32 n;\nmov.u32 n, 0;\n"
               "W_%=:\nmbarrier.try_wait.parity.shared::cta.b64 p, [%0], %1;\n@p bra D_%=;\n"
               "add.u32 n, n, 1;\nsetp.lt.u32 p, n, %2;\n@p bra W_%=;\ntrap;\nD_%=:\n}\n" ::"r"(bar), "r"(parity), "n"(SPIN_LIMIT) : "memory");
}
__device__ __forceinline__ void fence_async() { asm volatile("fence.proxy.async.shared::cta;" ::: "memory"); }
__device__ __forceinline__ void bar_sync(int id) { asm volatile("bar.sync %0, 128;" ::"r"(id) : "memory"); }
__device__ __forceinline__ void tma2d(uint32_t dst, const CUtensorMap* m, int c0, int c1, uint32_t bar) {
  asm volatile("cp.async.bulk.tensor.2d.shared::cluster.global.mbarrier::complete_tx::bytes [%0], [%1, {%3, %4}], [%2];"
               ::"r"(dst), "l"(m), "r"(bar), "r"(c0), "r"(c1) : "memory");
}
__device__ __forceinline__ void tma2d_mc(uint32_t dst, const CUtensorMap* m, int c0, int c1, uint32_t bar) {
  asm volatile("cp.async.bulk.tensor.2d.shared::cluster.global.mbarrier::complete_tx::bytes.multicast::cluster [%0], [%1, {%3, %4}], [%2], %5;"
               ::"r"(dst), "l"(m), "r"(bar), "r"(c0), "r"(c1), "h"((uint16_t)3) : "memory");
}
__device__ __forceinline__ void tma3d(uint32_t dst, const CUtensorMap* m, int c0, int c1, int c2, uint32_t bar) {
  asm volatile("cp.async.bulk.tensor.3d.shared::cluster.global.mbarrier::complete_tx::bytes [%0], [%1, {%3, %4, %5}], [%2];"
               ::"r"(dst), "l"(m), "r"(bar), "r"(c0), "r"(c1), "r"(c2) : "memory");
}
__device__ __forceinline__ void tma4d(uint32_t dst, const CUtensorMap* m, int c0, int c1, int c2, int c3, uint32_t bar) {
  asm volatile("cp.async.bulk.tensor.4d.shared::cluster.global.mbarrier::complete_tx::bytes [%0], [%1, {%3, %4, %5, %6}], [%2];"
               ::"r"(dst), "l"(m), "r"(bar), "r"(c0), "r"(c1), "r"(c2), "r"(c3) : "memory");
}
__device__ __forceinline__ void bulk_ld(uint32_t dst, const void* src, int bytes, uint32_t bar) {
  asm volatile("cp.async.bulk.shared::cluster.global.mbarrier::complete_tx::bytes [%0], [%1], %2, [%3];" ::"r"(dst), "l"(src), "r"(bytes), "r"(bar) : "memory");
}
__device__ __forceinline__ void bulk_ld_mc(uint32_t dst, const void* src, int bytes, uint32_t bar) {
  asm volatile("cp.async.bulk.shared::cluster.global.mbarrier::complete_tx::bytes.multicast::cluster [%0], [%1], %2, [%3], %4;"
               ::"r"(dst), "l"(src), "r"(bytes), "r"(bar), "h"((uint16_t)3) : "memory");
}
__device__ __forceinline__ void tma2d_st(const CUtensorMap* m, uint32_t src, int c0, int c1) {
  asm volatile("cp.async.bulk.tensor.2d.global.shared::cta.bulk_group [%0, {%2, %3}], [%1];" ::"l"(m), "r"(src), "r"(c0), "r"(c1) : "memory");
}
__device__ __forceinline__ void ldsm4(uint32_t (&r)[4], uint32_t a) {
  asm volatile("ldmatrix.sync.aligned.m8n8.x4.shared.b16 {%0,%1,%2,%3}, [%4];" : "=r"(r[0]), "=r"(r[1]), "=r"(r[2]), "=r"(r[3]) : "r"(a) : "memory");
}
__device__ __forceinline__ void ldsm4t(uint32_t (&r)[4], uint32_t a) {
  asm volatile("ldmatrix.sync.aligned.m8n8.x4.trans.shared.b16 {%0,%1,%2,%3}, [%4];" : "=r"(r[0]), "=r"(r[1]), "=r"(r[2]), "=r"(r[3]) : "r"(a) : "memory");
}
__device__ __forceinline__ void stsm4(uint32_t a, uint32_t r0, uint32_t r1, uint32_t r2, uint32_t r3) {
  asm volatile("stmatrix.sync.aligned.m8n8.x4.shared.b16 [%0], {%1,%2,%3,%4};" ::"r"(a), "r"(r0), "r"(r1), "r"(r2), "r"(r3) : "memory");
}
__device__ __forceinline__ uint32_t pk2(float lo, float hi) { uint32_t r; asm("cvt.rn.bf16x2.f32 %0, %1, %2;" : "=r"(r) : "f"(hi), "f"(lo)); return r; }
__device__ __forceinline__ uint32_t hmul(uint32_t a, uint32_t b) { uint32_t r; asm("mul.rn.bf16x2 %0, %1, %2;" : "=r"(r) : "r"(a), "r"(b)); return r; }
__device__ __forceinline__ uint32_t hadd(uint32_t a, uint32_t b) { uint32_t r; asm("add.rn.bf16x2 %0, %1, %2;" : "=r"(r) : "r"(a), "r"(b)); return r; }
__device__ __forceinline__ uint32_t hmin(uint32_t a, uint32_t b) { uint32_t r; asm("min.bf16x2 %0, %1, %2;" : "=r"(r) : "r"(a), "r"(b)); return r; }
__device__ __forceinline__ uint32_t hmaxabs(uint32_t a, uint32_t b) { uint32_t r; asm("max.xorsign.abs.bf16x2 %0, %1, %2;" : "=r"(r) : "r"(a), "r"(b)); return r; }
__device__ __forceinline__ float ex2(float x) { float r; asm("ex2.approx.ftz.f32 %0, %1;" : "=f"(r) : "f"(x)); return r; }
__device__ __forceinline__ float rcp_fast(float x) { float r; asm("rcp.approx.ftz.f32 %0, %1;" : "=f"(r) : "f"(x)); return r; }
__device__ __forceinline__ uint32_t phi2(float lo, float hi) {
  uint32_t t;
  asm("cvt.rn.relu.bf16x2.f32 %0, %1, %2;" : "=r"(t) : "f"(hi), "f"(lo));
  const uint32_t e = pk2(ex2(lo * 1.4426950408889634f), ex2(hi * 1.4426950408889634f));
  return hadd(hadd(t, hmin(e, 0x3F803F80u)), 0x35863586u);
}
__device__ __forceinline__ bool opaque_true() { uint32_t v; asm volatile("mov.u32 %0, %%nctaid.y;" : "=r"(v)); return v != 0; }
__device__ __forceinline__ int norm_exp(uint32_t (&v)[32], float f0) {
  uint32_t m[4] = {hmaxabs(__float_as_uint(f0) >> 16, v[0]), v[1], v[2], v[3]};
#pragma unroll
  for (int i = 4; i < 32; i++) m[i & 3] = hmaxabs(m[i & 3], v[i]);
  m[0] = hmaxabs(hmaxabs(m[0], m[1]), hmaxabs(m[2], m[3]));
  const int e = min(max((int)(__reduce_max_sync(~0u, max(m[0] & 0x7FFFu, (m[0] >> 16) & 0x7FFFu)) >> 7), 1), 253);
  if (e > 141) {
#pragma unroll
    for (int i = 0; i < 32; i++) v[i] = hmul(v[i], 0x07000700u);
  }
  return e;
}
__device__ __forceinline__ void norm_cvt(uint32_t (&v)[32], float f0, int e) {
  const uint32_t sc = (e > 141 ? 255 - e : 142 - e) * 0x00800080u;
#pragma unroll
  for (int i = 0; i < 32; i++) {
    const uint32_t a = hmul(v[i], sc);
    v[i] = (a & 0x0FFF0FFFu) * 7 + a;
  }
  v[0] = __byte_perm(v[0], __half_as_ushort(__float2half_rn(f0 * __uint_as_float((254 - e) << 23))), 0x3254);
}
__device__ __forceinline__ void poll_ge(const unsigned* p, unsigned target) {
#pragma unroll 1
  for (int n = 0; n < SPIN_LIMIT; n++) {
    unsigned v;
    asm volatile("ld.relaxed.gpu.global.u32 %0, [%1];" : "=r"(v) : "l"(p) : "memory");
    if (__all_sync(~0u, (int)(v - target) >= 0)) { asm volatile("fence.acquire.gpu;" ::: "memory"); return; }
  }
  __trap();
}

__device__ __forceinline__ bool elect_one() {
  uint32_t p;
  asm volatile("{\n.reg .pred p;\nelect.sync _|p, 0xffffffff;\nselp.u32 %0, 1, 0, p;\n}\n" : "=r"(p));
  return p;
}
__device__ __forceinline__ uint4 ld_na4(const void* p) {
  uint4 v;
  asm volatile("ld.global.L1::no_allocate.v4.u32 {%0,%1,%2,%3}, [%4];" : "=r"(v.x), "=r"(v.y), "=r"(v.z), "=r"(v.w) : "l"(p) : "memory");
  return v;
}
__device__ __forceinline__ void st_cg4(void* p, uint4 v) {
  asm volatile("st.global.cg.v4.u32 [%0], {%1,%2,%3,%4};" ::"l"(p), "r"(v.x), "r"(v.y), "r"(v.z), "r"(v.w) : "memory");
}
__device__ __forceinline__ uint32_t mapa(uint32_t a, uint32_t cta) { uint32_t r; asm("mapa.shared::cluster.u32 %0, %1, %2;" : "=r"(r) : "r"(a), "r"(cta)); return r; }
__device__ __forceinline__ void st_async(uint32_t a, uint32_t v, uint32_t bar) {
  asm volatile("st.async.weak.shared::cluster.mbarrier::complete_tx::bytes.b32 [%0], %1, [%2];" ::"r"(a), "r"(v), "r"(bar) : "memory");
}
__device__ __forceinline__ void st_async4(uint32_t a, uint32_t x, uint32_t y, uint32_t z, uint32_t w, uint32_t bar) {
  asm volatile("st.async.weak.shared::cluster.mbarrier::complete_tx::bytes.v4.b32 [%0], {%1,%2,%3,%4}, [%5];" ::"r"(a), "r"(x), "r"(y), "r"(z), "r"(w), "r"(bar) : "memory");
}
__device__ __forceinline__ void tma3d_st(const CUtensorMap* m, uint32_t src, int c0, int c1, int c2) {
  asm volatile("cp.async.bulk.tensor.3d.global.shared::cta.bulk_group [%0, {%2, %3, %4}], [%1];" ::"l"(m), "r"(src), "r"(c0), "r"(c1), "r"(c2) : "memory");
}
__device__ __forceinline__ uint4 ld_rlx4(const void* p) {
  uint4 v;
  asm volatile("{\n.reg .b128 t;\n.reg .b64 a, b;\nld.relaxed.gpu.global.b128 t, [%4];\nmov.b128 {a, b}, t;\nmov.b64 {%0, %1}, a;\nmov.b64 {%2, %3}, b;\n}\n"
               : "=r"(v.x), "=r"(v.y), "=r"(v.z), "=r"(v.w) : "l"(p) : "memory");
  return v;
}
__device__ __forceinline__ void ld_stale4(uint4& v, const void* p, uint32_t tag) {
  asm volatile("{\n.reg .b128 t;\n.reg .b64 a, b;\n.reg .b32 x;\n.reg .pred p;\n"
               "lop3.b32 x, %0, %5, 1, 0x28;\nsetp.ne.u32 p, x, 0;\n"
               "mov.b64 a, {%0, %1};\nmov.b64 b, {%2, %3};\nmov.b128 t, {a, b};\n"
               "@p ld.relaxed.gpu.global.b128 t, [%4];\n"
               "mov.b128 {a, b}, t;\nmov.b64 {%0, %1}, a;\nmov.b64 {%2, %3}, b;\n}\n"
               : "+r"(v.x), "+r"(v.y), "+r"(v.z), "+r"(v.w) : "l"(p), "r"(tag) : "memory");
}
__device__ __forceinline__ void st_tag4(void* p, float a, float b, float c, float d, uint32_t tag) {
  asm volatile("{\n.reg .b128 t;\n.reg .b64 a, b;\nmov.b64 a, {%1, %2};\nmov.b64 b, {%3, %4};\nmov.b128 t, {a, b};\nst.relaxed.gpu.global.b128 [%0], t;\n}\n"
               ::"l"(p), "r"((__float_as_uint(a) & ~1u) | tag), "f"(b), "f"(c), "f"(d) : "memory");
}
__device__ __forceinline__ uint32_t stale8(const uint4 (&f)[8], uint32_t tag) {
  uint32_t r[4];
#pragma unroll
  for (int i = 0; i < 4; i++) asm("lop3.b32 %0, %1, %2, %3, 0x7E;" : "=r"(r[i]) : "r"(f[2 * i].x), "r"(f[2 * i + 1].x), "r"(tag));
  asm("lop3.b32 %0, %0, %1, %2, 0xFE;" : "+r"(r[0]) : "r"(r[1]), "r"(r[2]));
  return r[0] | r[3];
}

struct ConvC { uint32_t a1[2][4], wa[2], wb[2], sg; };
__device__ __forceinline__ uint64_t dsc(uint32_t lo, uint32_t hi) { return ((uint64_t)hi << 32) | lo; }
__device__ __forceinline__ uint32_t hfma(uint32_t a, uint32_t b, uint32_t c) { uint32_t r; asm("fma.rn.f16x2 %0, %1, %2, %3;" : "=r"(r) : "r"(a), "r"(b), "r"(c)); return r; }
__device__ __forceinline__ uint32_t hfnma(uint32_t a, uint32_t b, uint32_t c) { uint32_t r; asm("{.reg .b32 n; neg.f16x2 n, %1; fma.rn.f16x2 %0, n, %2, %3;}" : "=r"(r) : "r"(a), "r"(b), "r"(c)); return r; }
__device__ __forceinline__ uint32_t hmul16(uint32_t a, uint32_t b) { uint32_t r; asm("mul.rn.f16x2 %0, %1, %2;" : "=r"(r) : "r"(a), "r"(b)); return r; }
template <int N> __device__ __forceinline__ void keepu(uint32_t (&d)[N]) {
#pragma unroll
  for (int i = 0; i < N; i++) asm volatile("" : "+r"(d[i])::"memory");
}
__device__ __forceinline__ void conv_m1(const ConvC& K, uint32_t (&u)[16], uint32_t l) {
  wg_fence();
  wgmma_hrs_n64<1>(u, K.a1[0][0], K.a1[0][1], K.a1[0][2], K.a1[0][3], dsc(l, 32), 0);
  wgmma_hrs_n64<1>(u, K.a1[1][0], K.a1[1][1], K.a1[1][2], K.a1[1][3], dsc(l + 16, 32), 1);
  wg_commit();
}
__device__ __forceinline__ void conv_s2(const ConvC& K, uint32_t (&u)[16], uint32_t (&Z)[2][8], uint32_t dfl) {
  uint32_t fr[8], fi[8];
#pragma unroll
  for (int c = 0; c < 8; c++) {
    const uint32_t r = hfma(K.wa[c & 1], u[2 * c + 1], u[2 * c]);
    fi[c] = hfma(K.wb[c & 1], r, u[2 * c + 1]);
    fr[c] = hfma(K.wa[c & 1], fi[c], r);
  }
  wg_fence();
#pragma unroll
  for (int p = 0; p < 2; p++) {
    wgmma_hrs_n32<0>(Z[p], fr[4 * p], fr[4 * p + 2], fr[4 * p + 1], fr[4 * p + 3], dsc(dfl, 32), 0);
    wgmma_hrs_n32<0>(Z[p], fi[4 * p], fi[4 * p + 2], fi[4 * p + 1], fi[4 * p + 3], dsc(dfl + 16, 32), 1);
  }
  wg_commit();
}
__device__ __forceinline__ void conv_win(const ConvC& K, const uint32_t (&X)[2][8], uint32_t (&W)[2][8]) {
#pragma unroll
  for (int b = 0; b < 4; b++)
#pragma unroll
    for (int c = 0; c < 2; c++) {
      const uint32_t xr = X[b >> 1][2 * c + (b & 1)], xi = X[b >> 1][4 + 2 * c + (b & 1)];
      const int a = b ? b - 1 : 0;
      W[b >> 1][2 * c + (b & 1)] = b ? hfnma(K.sg, X[a >> 1][4 + 2 * c + (a & 1)], xr) : hmul16(xr, 0x3C003C00u);
      W[b >> 1][4 + 2 * c + (b & 1)] = b ? hfma(K.sg, X[a >> 1][2 * c + (a & 1)], xi) : hmul16(xi, 0x3C003C00u);
    }
}
template <int p>
__device__ __forceinline__ void conv_pw(uint32_t (&X)[2][8], uint32_t (&H)[2][8], uint32_t (&V)[8], uint32_t dil) {
  uint32_t pr[2][2], pi[2][2];
#pragma unroll
  for (int jj = 0; jj < 2; jj++)
#pragma unroll
    for (int c = 0; c < 2; c++) {
      const int j = 2 * p + jj;
      uint32_t sr = 0, si = 0;
#pragma unroll
      for (int a = 0; a <= j; a++) {
        const int b = j - a;
        const uint32_t hr = H[a >> 1][2 * c + (a & 1)], hi = H[a >> 1][4 + 2 * c + (a & 1)];
        const uint32_t xr = X[b >> 1][2 * c + (b & 1)], xi = X[b >> 1][4 + 2 * c + (b & 1)];
        sr = a == 0 ? hmul16(hr, xr) : hfma(hr, xr, sr);
        si = a == 0 ? hmul16(hr, xi) : hfma(hr, xi, si);
        sr = hfnma(hi, xi, sr);
        si = hfma(hi, xr, si);
      }
      pr[jj][c] = sr; pi[jj][c] = si;
    }
  wg_fence();
  wgmma_hrs_n32<0>(V, pr[0][0], pr[1][0], pr[0][1], pr[1][1], dsc(dil, 32), 0);
  wgmma_hrs_n32<0>(V, pi[0][0], pi[1][0], pi[0][1], pi[1][1], dsc(dil + 16, 32), 1);
  wg_commit();
}
template <int p>
__device__ __forceinline__ void conv_it(const ConvC& K, uint32_t (&V)[8], uint32_t vst) {
#pragma unroll
  for (int jj = 0; jj < 2; jj++) {
    uint32_t wr[2], wi[2];
#pragma unroll
    for (int c = 0; c < 2; c++) {
      const uint32_t r = hfnma(K.wa[c], V[4 + 2 * c + jj], V[2 * c + jj]);
      wi[c] = hfnma(K.wb[c], r, V[4 + 2 * c + jj]);
      wr[c] = hfnma(K.wa[c], wi[c], r);
    }
    stsm4(vst + (2 * p + jj) * 2048, wr[0], wr[1], wi[0], wi[1]);
  }
}
__device__ __forceinline__ void conv_m4(uint32_t (&y)[8], uint32_t (&a)[4][4], uint32_t d4l) {
  wg_fence();
  wgmma_hrs_n32<0>(y, a[0][0], a[0][1], a[0][2], a[0][3], dsc(d4l, 64), 0);
#pragma unroll
  for (int s = 1; s < 4; s++) wgmma_hrs_n32<0>(y, a[s][0], a[s][1], a[s][2], a[s][3], dsc(d4l + s * 16, 64), 1);
  wg_commit();
}

struct Params {
  CUtensorMap tmX0, tmW, tmX, tmWo, tmWo1, tmK, tmV, tmQ, tmOA, tmOB;
  const __nv_bfloat16 *shift_k, *h, *D, *x, *w, *wo, *q;
  float *part, *kv;
  uint4* o;
  const uint32_t *thr, *img;
};

__global__ void __cluster_dims__(2, 1, 1) __launch_bounds__(384, 1) fused_kernel(const __grid_constant__ Params P) {
  extern __shared__ __align__(1024) uint8_t smem[];
#define MAP_PF(m) asm volatile("prefetch.tensormap [%0];" ::"l"(&P.m) : "memory")
  if (threadIdx.x == 0) { MAP_PF(tmX0); MAP_PF(tmW); MAP_PF(tmX); }
  const uint32_t sb = __shfl_sync(~0u, smem_u32(smem), 0);
  const uint32_t bars = sb + OFF_BAR;
  const int tid = threadIdx.x, lane = tid & 31;
  const int warp = __shfl_sync(~0u, tid >> 5, 0);
  const int rank = blockIdx.x & 1, pc = blockIdx.x >> 1;
  const unsigned c7 = pc + 6, g7 = (c7 * 37) >> 8;
  const int mb = pc < 4 ? 4 + pc : pc < 36 ? (pc - 4) >> 3 : g7 - 2;
  const int hq = pc < 4 ? 0 : pc < 36 ? (pc - 4) & 7 : 1 + c7 - 7 * g7;
  const int cl = 8 * hq + mb;
  const int hp = 2 * hq + rank;
  const int rb = 2 * mb + (hq >> 2), cb = hq & 3;
#define BAR(i) (bars + 8 * (i))
#define OCNT(rb, hh) ((unsigned*)(P.o + (rb) * OBLK + 16 * 1024 + 8 * (hh)))
#define EPOCH (OCNT(rb, 2)[hp & 7])

  if (tid == 0) { STAMP(0, 0); GSTAMP(0, 30); }
  if (warp == 8) {
    if (elect_one()) {
      mbar_init(BAR(B_FIRST), 1);
      asm volatile("fence.mbarrier_init.release.cluster;" ::: "memory");
      mbar_expect(BAR(B_FIRST), STAGE_BYTES - 16384);
      tma2d(sb, &P.tmX0, 0, mb * 256, BAR(B_FIRST));
      tma2d(sb + 16384, &P.tmX0, 0, mb * 256 + 128, BAR(B_FIRST));
      tma3d(sb + 32768, &P.tmW, hp * 64, 0, 0, BAR(B_FIRST));
      mbar_init(BAR(B_FULL1), 1);
      asm volatile("fence.mbarrier_init.release.cluster;" ::: "memory");
    }
    if (lane == 0) STAMP(3, 21);
  } else if (lane == 0) {
    const int wi = warp - (warp > 8);
#pragma unroll
    for (int r = 0; r < 6; r++)
      if (r < 5 || wi < B_COUNT - 56) mbar_init(BAR(1 + 11 * r + wi), ((uint32_t)(bar_counts(r) >> (4 * wi)) & 15) + 1);
    asm volatile("fence.mbarrier_init.release.cluster;" ::: "memory");
  }
  if (tid == 0) STAMP(2, 6);
  asm volatile("barrier.cluster.arrive.relaxed.aligned;\nbarrier.cluster.wait.aligned;" ::: "memory");
  if (warp == 8 && elect_one()) {
    mbar_expect(BAR(B_FULL1), 16384);
    tma2d_mc(sb + 8192 + rank * 16384, &P.tmX0, 0, mb * 256 + 64 + rank * 128, BAR(B_FULL1));
  }
  if (tid == 256) STAMP(2, 7);

  if (warp < 8) {
    asm volatile("setmaxnreg.inc.sync.aligned.u32 224;");
    const int wg = warp >> 2, w = warp & 3, g = lane >> 2, q = lane & 3, t = tid & 127;
    const bool elect = (t == 0);
    const uint32_t s16 = (sb & 0x3FFFF) >> 4;
    uint32_t pq[2][16], ux[16], uh[16], X[4][2][8], H[4][2][8];
    ConvC K;
    const uint32_t dfl = s16 + (OFF_F2F >> 4) + (8 << 16), dil = s16 + (OFF_F2I >> 4) + (8 << 16), d4l = s16 + (OFF_F4 >> 4) + (8 << 16);
    const uint32_t xl = s16 + (OFF_XT >> 4) + 4 * wg * (XT_STRIDE >> 4) + (8 << 16);
    const uint32_t hl = s16 + (OFF_H >> 4) + wg * 512 + (8 << 16);
    {
      float acc[2][96];
      {
#pragma unroll
        for (int mt = 0; mt < 2; mt++) {
          mbar_wait(BAR(mt ? B_FULL1 : B_FIRST), 0);
          if (mt == 0 && elect) { STAMP(wg, 1); GSTAMP(wg, 26); }
          wg_fence();
#pragma unroll
          for (int ks = 0; ks < 4; ks++)
            wgmma_ss_n192<0, 1>(acc[mt], dsc(s16 + wg * 1024 + mt * 512 + (1 << 16) + ks * 2, SW128), dsc(s16 + 2048 + (512 << 16) + ks * 128, SW128), ks != 0);
        }
        wg_commit();
      }
      int st = 1, ph = 0;
#pragma unroll 1
      for (int kb = 1; kb < 14; kb++) {
        mbar_wait(BAR(B_FULL1 + st), ph);
        if (kb == 8 && elect) { STAMP(wg, 16); GSTAMP(wg, 25); }
        const uint32_t da = s16 + st * (STAGE_BYTES >> 4) + wg * 1024 + (1 << 16);
        const uint32_t db = s16 + st * (STAGE_BYTES >> 4) + 2048 + (512 << 16);
        wg_fence();
#pragma unroll
        for (int ks = 0; ks < 4; ks++) {
          wgmma_ss_n192<0, 1>(acc[0], dsc(da + ks * 2, SW128), dsc(db + ks * 128, SW128), 1);
          wgmma_ss_n192<0, 1>(acc[1], dsc(da + 512 + ks * 2, SW128), dsc(db + ks * 128, SW128), 1);
        }
        wg_commit();
        wg_wait<1>();
        if (t < 2) mbar_arrive_cl(BAR(B_EMPTY1 + (st == 0 ? 2 : st - 1)), t);
        if (++st == 3) { st = 0; ph ^= 1; }
      }
#define TAIL_MMA(mt, stage) do { wg_fence(); _Pragma("unroll") for (int ks = 0; ks < 4; ks++) \
        wgmma_ss_n192<0, 1>(acc[mt], dsc(s16 + (stage) * (STAGE_BYTES >> 4) + wg * 1024 + (mt) * 512 + (1 << 16) + ks * 2, SW128), \
                            dsc(s16 + (stage) * (STAGE_BYTES >> 4) + 2048 + (512 << 16) + ks * 128, SW128), 1); wg_commit(); } while (0)
      mbar_wait(BAR(B_FULL1 + 2), 0);
      TAIL_MMA(0, 2);
      wg_wait<1>();
      if (elect) mbar_arrive(BAR(B_SFREE));
      mbar_wait(BAR(B_FULL1 + 0), 1);
      TAIL_MMA(0, 0);
      TAIL_MMA(1, 2);
      const uint32_t lrow = sb + wg * 16384 + (16 * w + 8 * ((lane >> 3) & 1) + (lane & 7)) * 128 + (((lane >> 4) ^ (lane & 7)) << 4);
#define E1K(mt, i) do { if (opaque_true()) { _Pragma("unroll") for (int j = (i); j < (i) + 2; j++) { \
          const float* a = &acc[mt][32 + 8 * j]; const float* b = a + 32; const uint32_t o = (lrow ^ (j * 32)) + (mt) * 8192; \
          stsm4(o + 2 * STAGE_BYTES, pk2(b[0], b[1]), pk2(b[2], b[3]), pk2(b[4], b[5]), pk2(b[6], b[7])); \
          stsm4(o, phi2(a[0], a[1]), phi2(a[2], a[3]), phi2(a[4], a[5]), phi2(a[6], a[7])); } } } while (0)
#define E1Q(mt) do { if (opaque_true()) { _Pragma("unroll") for (int i = 0; i < 16; i++) pq[mt][i] = phi2(acc[mt][2 * i], acc[mt][2 * i + 1]); } } while (0)
#define LOAD_K() do { const uint4* ct = (const uint4*)P.thr + t; \
        _Pragma("unroll") for (int s = 0; s < 2; s++) { const uint4 u = ld_na4(ct + s * 128); K.a1[s][0] = u.x; K.a1[s][1] = u.y; K.a1[s][2] = u.z; K.a1[s][3] = u.w; } \
        const uint4 u = ld_na4(ct + 2 * 128); K.wa[0] = u.x; K.wa[1] = u.y; K.wb[0] = u.z; K.wb[1] = u.w; \
        K.sg = (lane & 4) ? 0xBC00BC00u : 0x3C003C00u; } while (0)
#define PK_READY(mt) do { fence_async(); __syncwarp(); if (lane == 0) mbar_arrive(BAR(B_PKRDY + (mt))); } while (0)
      wg_wait<1>();
      keep(acc[0]);
      if (elect) STAMP(wg, 18);
      E1K(0, 0);
      TAIL_MMA(1, 0);
      E1K(0, 2);
      if (elect) STAMP(wg, 19);
      PK_READY(0);
      wg_wait<0>();
      keep(acc[1]);
      if (elect) mbar_arrive(BAR(B_G1DONE));
      asm volatile("setmaxnreg.dec.sync.aligned.u32 %0;" ::"n"(RC));
      if (elect) { STAMP(wg, 2); GSTAMP(wg, 27); }
      E1K(1, 0);
      if (elect) STAMP(wg, 20);
      E1K(1, 2);
      if (elect) STAMP(wg, 21);
      PK_READY(1);
      if (elect) STAMP(wg, 3);
      LOAD_K();
      if (elect) STAMP(wg, 4);
      E1Q(0);
      E1Q(1);
      if (elect) STAMP(wg, 17);
      mbar_wait(BAR(B_H), 0);
      conv_m1(K, ux, xl);
      conv_m1(K, uh, hl);
      wg_wait<1>(); keepu(ux);
      if (lane == 0) mbar_arrive_cl(BAR(B_XFREE + 4 * wg), rank ^ 1);
      conv_s2(K, ux, X[0], dfl);
      wg_wait<1>(); keepu(uh);
      conv_s2(K, uh, H[0], dfl);
    }
    if (elect) STAMP(wg, 5);
    float acc[64];
#define G2_MMA(da, db, first) do { wg_fence(); _Pragma("unroll") for (int ks = 0; ks < 4; ks++) \
        wgmma_ss_n128<0, 1>(acc, dsc((da) + ks * 2, SW128), dsc((db) + ks * 128, SW128), ks || !(first)); wg_commit(); } while (0)
    const uint32_t a0 = s16 + wg * 512 + (1 << 16), b0 = s16 + (512 << 16);
    uint32_t cons = mapa(BAR(B_CONS2 - 1 + G2E), t & 1);
    const bool rel = __shfl_sync(~0u, t, lane) < 2;
    {
      uint32_t vst = sb + wg * 8192 + w * 512 + lane * 16, vld = sb + wg * 8192 + w * 2048 + lane * 16;
      uint32_t ya = mapa(sb + OFF_XT + 4 * wg * XT_STRIDE + (2 * rank + (w & 1)) * 1024 + lane * 16, w >> 1);
      const uint32_t ybar = mapa(BAR(B_Y), w >> 1);
      asm volatile("" : "+r"(vst), "+r"(vld), "+r"(ya));
      uint32_t W[2][8], V0[8], V1[8], y[8], a[4][4];
      uint4 ov[4];
      uint4* const ot = P.o + (2 * mb + wg) * OBLK + hq * 1024 + (16 * w + g) * 8 + ((4 * rank + q) ^ g);
#define YOUT(i) do { if ((w >> 1) == rank) { \
          asm volatile("st.shared.v4.b32 [%0], {%1,%2,%3,%4};" ::"r"(ya + (i) * XT_STRIDE), "r"(y[0]), "r"(y[2]), "r"(y[4]), "r"(y[6]) : "memory"); \
          asm volatile("st.shared.v4.b32 [%0], {%1,%2,%3,%4};" ::"r"(ya + (i) * XT_STRIDE + 512), "r"(y[1]), "r"(y[3]), "r"(y[5]), "r"(y[7]) : "memory"); \
        } else { \
          mbar_wait(BAR(B_XFREE + 4 * wg + (i)), 0); \
          st_async4(ya + (i) * XT_STRIDE, y[0], y[2], y[4], y[6], ybar); \
          st_async4(ya + (i) * XT_STRIDE + 512, y[1], y[3], y[5], y[7], ybar); } } while (0)
      auto ocalc = [&](const int hh) {
        if (hh == 0) {
          if (elect) STAMP(wg, 8);
          mbar_wait(BAR(B_KV), 0);
          if (elect) STAMP(wg, 9);
        } else mbar_wait(BAR(B_KV1), 0);
        float oa[2][20];
        wg_fence();
#pragma unroll
        for (int m = 0; m < 4; m++) {
          const uint32_t* p = &pq[m & 1][8 * hh + 4 * (m >> 1)];
          wgmma_rs_n40<1>(oa[m & 1], p[0], p[1], p[2], p[3], dsc(s16 + (OFF_KVB >> 4) + hh * 160 + (m >> 1) * 16 + (8 << 16), 32), m >> 1);
        }
        wg_commit();
        wg_wait<0>();
#pragma unroll
        for (int mt = 0; mt < 2; mt++) {
          float (&o)[20] = oa[mt];
          keep(o);
          const uint32_t den = hadd(pk2(o[16], o[18]), 0x35863586u);
#pragma unroll
          for (int r = 0; r < 2; r++) {
            const float ri = rcp_fast(__uint_as_float(r ? (den & 0xFFFF0000u) : (den << 16)));
            uint4 u;
            u.x = pk2(o[2 * r] * ri, o[2 * r + 1] * ri);
            u.y = pk2(o[4 + 2 * r] * ri, o[5 + 2 * r] * ri);
            u.z = pk2(o[8 + 2 * r] * ri, o[9 + 2 * r] * ri);
            u.w = pk2(o[12 + 2 * r] * ri, o[13 + 2 * r] * ri);
            if (hh == 0) st_cg4(ot + (64 * mt + 8 * r) * 8, u); else ov[2 * mt + r] = u;
          }
        }
        if (hh == 0) {
          __syncwarp();
          if (lane == 0) mbar_arrive(BAR(B_ODONE));
          if (elect) STAMP(wg, 10);
        }
      };
      auto trickle = [&](const int qs) {
        const int m = qs - 2 * (OCH + O1D) - (TRICK - 1);
        if (m >= 0 && m < 4) {
          st_cg4(ot + 8 * 1024 + (64 * (m >> 1) + 8 * (m & 1)) * 8, ov[m]);
          if (m == 3) { __syncwarp(); if (lane == 0) mbar_arrive(BAR(B_ODONE1)); }
        }
      };
#pragma unroll
      for (int i = 0; i < 4; i++) {
        const bool nx = i < 3;
        const int n = nx ? i + 1 : i;
        const uint32_t vo = (i & 1) ? OFF_H + (i >> 1) * 16384 : OFF_VP;
        if (2 * i == OCH) ocalc(0);
        if (2 * i == OCH + O1D) ocalc(1);
        if (nx) {
          conv_m1(K, ux, xl + n * (XT_STRIDE >> 4));
          conv_m1(K, uh, hl + (n >> 1) * 1024 + (n & 1) * 256);
        }
        if (2 * i != OCH && 2 * i != OCH + O1D) { if (nx) { if (i > 0) wg_wait<3>(); else wg_wait<2>(); } else wg_wait<1>(); }
        keepu(X[i][0]); keepu(X[i][1]); keepu(H[i][0]); keepu(H[i][1]);
        conv_win(K, X[i], W);
        trickle(4 * i);
        conv_pw<0>(W, H[i], V0, dil);
        conv_pw<1>(W, H[i], V1, dil);
        trickle(4 * i + 1);
        wg_wait<2>();
        if (i > 0) { keepu(y); YOUT(i - 1); }
        if (2 * i + 1 == OCH) ocalc(0);
        if (2 * i + 1 == OCH + O1D) ocalc(1);
        if (nx) {
          keepu(ux); keepu(uh);
          if (lane == 0) mbar_arrive_cl(BAR(B_XFREE + 4 * wg + n), rank ^ 1);
          conv_s2(K, ux, X[n], dfl);
          wg_wait<1>();
        } else wg_wait<0>();
        keepu(V0); keepu(V1);
        if (G2E && G2P == 0 && i == 3) { mbar_wait(BAR(B_FULL2), 0); G2_MMA(a0 + (SLOT_A & 15) * 1024, b0 + (SLOT_B & 15) * 1024, true); }
        trickle(4 * i + 2);
        if (i == 0) mbar_wait(BAR(B_H2), 0);
        conv_it<0>(K, V0, vst + vo);
        conv_it<1>(K, V1, vst + vo);
        if (G2E && G2P == 1 && i == 3) { mbar_wait(BAR(B_FULL2), 0); G2_MMA(a0 + (SLOT_A & 15) * 1024, b0 + (SLOT_B & 15) * 1024, true); }
        bar_sync(1 + wg);
#pragma unroll
        for (int s = 0; s < 4; s++) ldsm4t(a[s], vld + vo + s * 512);
        if (nx) conv_s2(K, uh, H[n], dfl);
        conv_m4(y, a, d4l);
        trickle(4 * i + 3);
        if (i > 0 && lane < 2) mbar_arrive_cl(BAR(B_AFREE + i - 1), lane);
        if (elect && i < 3) STAMP(wg, i < 2 ? 6 + i : 9 + i);
      }
      if (G2E && G2P == 2) { mbar_wait(BAR(B_FULL2), 0); G2_MMA(a0 + (SLOT_A & 15) * 1024, b0 + (SLOT_B & 15) * 1024, true); wg_wait<1>(); }
      else wg_wait<0>();
      keepu(y);
      if (G2E && G2P < 2 && rel) asm volatile("mbarrier.arrive.shared::cluster.b64 _, [%0];" ::"r"(cons) : "memory");
      YOUT(3);
      __syncwarp();
      if (lane == 0) mbar_arrive(BAR(B_Y));
      if (elect) STAMP(wg, 12);
    }
    {
      uint64_t ta = SLOT_A >> (4 * G2E), tb = SLOT_B >> (4 * G2E);
      uint32_t da = a0 + ((uint32_t)ta & 15) * 1024, db = b0 + ((uint32_t)tb & 15) * 1024, fb = BAR(B_FULL2 + G2E);
#pragma unroll 1
      for (int kb = G2E; kb < HOLD2; kb++) {
        mbar_wait(fb, 0);
        G2_MMA(da, db, kb == 0);
        ta >>= 4; tb >>= 4;
        da = a0 + ((uint32_t)ta & 15) * 1024; db = b0 + ((uint32_t)tb & 15) * 1024; fb += 8;
        asm volatile("" : "+r"(da), "+r"(db));
        wg_wait<1>();
        if ((kb > G2E || (G2E && G2P == 2)) && kb < 12 && rel) asm volatile("mbarrier.arrive.shared::cluster.b64 _, [%0];" ::"r"(cons) : "memory");
        cons += 8;
      }
#pragma unroll
      for (int kb = HOLD2; kb < 16; kb++) {
        if (wg == 1) mbar_wait(BAR(B_FULL2 + kb), 0);
        else if (kb == HOLD2) asm volatile("bar.sync 3, 256;" ::: "memory");
        G2_MMA(a0 + ((SLOT_A >> (4 * kb)) & 15) * 1024, b0 + ((SLOT_B >> (4 * kb)) & 15) * 1024, false);
      }
      if (wg == 1) asm volatile("bar.arrive 3, 256;" ::: "memory");
      const uint32_t stg = sb + wg * 8192 + w * 2048, so0 = ((SLOT_A >> 56) & 15) * 16384, so1 = ((SLOT_A >> 60) & 15) * 16384;
      const uint32_t lrow = stg + (8 * ((lane >> 3) & 1) + (lane & 7)) * 128 + (((lane >> 4) ^ (lane & 7)) << 4);
      const int col = 1024 + 256 * cb + 128 * rank, row = 128 * rb + 64 * wg + 16 * w;
      wg_wait<0>();
      keep(acc);
      if (elect) { STAMP(wg, 14); GSTAMP(wg, 29); }
#pragma unroll
      for (int cp = 0; cp < 8; cp++) {
        const float* a = &acc[8 * cp];
        stsm4((lrow ^ ((cp & 3) * 32)) + (cp >> 2 ? so1 : so0), pk2(a[0], a[1]), pk2(a[2], a[3]), pk2(a[4], a[5]), pk2(a[6], a[7]));
        if ((cp & 3) == 3) {
          fence_async();
          __syncwarp();
          if (elect_one()) tma2d_st(&P.tmOB, stg + (cp >> 2 ? so1 : so0), col + (cp >> 2) * 64, row);
        }
      }
      asm volatile("cp.async.bulk.commit_group;\ncp.async.bulk.wait_group.read 0;" ::: "memory");
      if (elect) {
        STAMP(wg, 15); GSTAMP(wg, 31); PDUMP(wg); if (wg == 0) PDUMP(2);
      }
    }
  } else {
    asm volatile("setmaxnreg.dec.sync.aligned.u32 56;");
    const int hw = warp - 9, g = lane >> 2, q = lane & 3;
#define sbar (bars + 8 * (B_STG - 18) + 16 * warp)
    if (warp == 8) {
      if (D1) __nanosleep(D1);
      int st = 1, pp = 1;
      const uint8_t* pfx = (const uint8_t*)P.x + (mb * 256 + hp * 16 + (lane & 15)) * 2048;
      const uint8_t* pfw = (const uint8_t*)P.w + (mb * 8 + (lane & 7)) * 6144 + (lane >> 3) * 2048 + hp * 128;
#pragma unroll 1
      for (int kb = 1; kb < 16; kb++) {
        if (kb >= 3) mbar_wait(BAR(B_EMPTY1 + st), pp);
        const uint32_t sa = sb + st * STAGE_BYTES;
        if (elect_one()) {
          mbar_expect(BAR(B_FULL1 + st), STAGE_BYTES);
          tma2d_mc(sa + rank * 16384, &P.tmX, kb * 64, mb * 256 + rank * 128, BAR(B_FULL1 + st));
          tma3d(sa + 32768, &P.tmW, hp * 64, kb * 64, 0, BAR(B_FULL1 + st));
        }
        if (kb == 1 && lane == 0) STAMP(2, 24);
        if (PFD && kb >= 2) {
#pragma unroll 1
          for (int j = kb == 2 ? 3 : kb + PFD; j <= kb + PFD && j < 16; j++) {
            if (lane < 16) asm volatile("prefetch.global.L2 [%0];" ::"l"(pfx + j * 128));
            if (lane < 24) asm volatile("prefetch.global.L2 [%0];" ::"l"(pfw + j * (64 * 6144)));
          }
          if (kb >= QPF && kb < QPF + 8) asm volatile("prefetch.global.L2 [%0];" ::"l"((const uint8_t*)P.q + (blockIdx.x * 256 + (kb - QPF) * 32 + lane) * 128));
          if (kb >= 4)
            asm volatile("prefetch.global.L2 [%0];" ::"l"(kb < 12 ? (const uint8_t*)P.h + ((2 * cl + rank) * 256 + (kb - 4) * 32 + lane) * 128
                                                                  : (const uint8_t*)P.wo + (blockIdx.x * 128 + (kb - 12) * 32 + lane) * 128));
        }
        if (++st == 3) { st = 0; pp ^= 1; }
      }
      if (elect_one()) { MAP_PF(tmWo); MAP_PF(tmWo1); }
      if (lane == 0) STAMP(2, 1);
    } else {
      {
        const uint32_t clk0 = __shfl_sync(~0u, (uint32_t)clock(), 0), stg = sb + OFF_STG + hw * STG_STRIDE;
        const unsigned epoch = __shfl_sync(~0u, EPOCH, 0);
        const uint32_t tag = ~epoch & 1;
        uint32_t tap[2][4];
#pragma unroll
        for (int cg = 0; cg < 2; cg++) {
          const uint2 u = __ldg((const uint2*)(P.shift_k + (16 * cl + 8 * cg + g) * 4));
          tap[cg][0] = __byte_perm(u.x, 0, 0x1010); tap[cg][1] = __byte_perm(u.x, 0, 0x3232);
          tap[cg][2] = __byte_perm(u.y, 0, 0x1010); tap[cg][3] = __byte_perm(u.y, 0, 0x3232);
        }
        if (hw == 0 && lane < 8) *(float*)(smem + OFF_D + 4 * lane) = __bfloat162float(P.D[16 * cl + 8 * rank + lane]);
        if (hw == 1 && lane < 24) asm volatile("prefetch.global.L2 [%0];" ::"l"(P.thr + (lane + 24 * rank) * 32));
        if (hw == 0 && elect_one()) {
          *(volatile unsigned*)(smem + OFF_EPOCH) = epoch;
          mbar_expect(BAR(B_XRAW), 16384);
          mbar_expect(BAR(B_Y), 16384 + 64);
        }
#pragma unroll 1
        for (int i = hw * 32 + lane; i < 528; i += 96) st_tag4(P.part + (hp * 8 + mb) * 2176 + 4 * i, 0.f, 0.f, 0.f, 0.f, tag ^ 1);
        if (hw < 2 || lane < 2) st_tag4(P.kv + hp * 2176 + (4 * (hw < 2 ? 64 * mb + 32 * hw + lane : 512 + 8 * (mb & 1) + (mb & 6) + lane)), 0.f, 0.f, 0.f, 0.f, tag ^ 1);
        if (lane == 0) STAMP(3, hw);
        const uint32_t xo = sb + OFF_XT + g * XT_STRIDE + rank * 2048 + q * 4;
        const int krow = 8 + (lane & 7) - (lane >> 3);
        const uint32_t ka = stg + krow * 32 + ((krow & 4) << 2), va = stg + 2304 + lane * 32 + ((lane & 4) << 2);
        int ph = 0, b = 0;
#pragma unroll 1
        for (int ci = hw - 3; ci < 16; ci += 3) {
          const uint32_t bo = b ? OFF_F2F - OFF_STG : 0, bn = b ? 0 : OFF_F2F - OFF_STG;
          if (ci + 3 < 16) {
            while (__any_sync(~0u, (uint32_t)clock() - clk0 < HSTART + (ci + 3) * PACE)) __nanosleep(64);
            if (elect_one()) {
              mbar_expect(sbar + 8 * (b ^ 1), 2304 + 2048);
              tma2d(stg + bn, &P.tmK, 16 * cl, 1024 * rank + 64 * (ci + 3) - 8, sbar + 8 * (b ^ 1));
              tma2d(stg + bn + 2304, &P.tmV, 16 * cl, 1024 * rank + 64 * (ci + 3), sbar + 8 * (b ^ 1));
            }
          }
          if (ci >= 0) {
            mbar_wait(sbar + 8 * b, (ph >> b) & 1);
            ph ^= 1 << b;
#pragma unroll 1
            for (int grp = 0; grp < 2; grp++) {
#pragma unroll
              for (int cg = 0; cg < 2; cg++) {
                const uint32_t dst = mapa(xo + (ci >> 3) * 1024 + ((ci & 7) * 4 + 2 * grp) * 16, cg), xbar = mapa(BAR(B_XRAW), cg);
                uint32_t vv[4], kk[4][4];
                ldsm4t(vv, (va ^ (cg * 16)) + bo + grp * 1024);
#pragma unroll
                for (int rg = 0; rg < 4; rg++) ldsm4t(kk[rg], (ka ^ (cg * 16)) + bo + grp * 1024 + rg * 256);
#pragma unroll
                for (int rg = 0; rg < 4; rg++)
                  vv[rg] = hmul(hadd(hadd(hadd(hmul(kk[rg][3], tap[cg][3]), hmul(kk[rg][2], tap[cg][2])), hmul(kk[rg][1], tap[cg][1])), hmul(kk[rg][0], tap[cg][0])), vv[rg]);
                if (cg == rank) {
#pragma unroll
                  for (int rg = 0; rg < 4; rg++) asm volatile("st.shared.b32 [%0], %1;" ::"r"(dst + (rg & 1) * 512 + (rg >> 1) * 16), "r"(vv[rg]) : "memory");
                } else {
#pragma unroll
                  for (int rg = 0; rg < 4; rg++) st_async(dst + (rg & 1) * 512 + (rg >> 1) * 16, vv[rg], xbar);
                }
              }
            }
          }
          b ^= 1;
        }
      }
      if (lane == 0 && hw == 0) STAMP(3, 3);
      asm volatile("bar.sync 4, 96;" ::: "memory");
      if (hw == 0 && elect_one()) { mbar_expect(BAR(B_XT), 10240); bulk_ld(sb + OFF_F2F, P.img, 10240, BAR(B_XT)); }
      mbar_wait(BAR(B_XRAW), 0);
    }
    int e1 = 0;
#pragma unroll 1
    for (int n = hw < 0 ? 3 : 0; n < 4; n++) {
      const bool isH = n >= 3;
      const int c = isH ? (warp & 1) + 2 * (warp & 2) : hw + 3 * n;
      if (c < 8) {
        int ln;
        asm volatile("mov.u32 %0, %%laneid;" : "=r"(ln));
        uint8_t* dst = smem + (isH ? OFF_H + (c & 2) * 8192 + (c >> 2) * 8192 + (c & 1) * 4096 : OFF_XT + c * XT_STRIDE) + ((ln >> 4) * 512 + (ln & 15) * 16);
        const uint8_t* src0 = isH ? (const uint8_t*)P.h + (16 * cl + 8 * rank + c) * 4096 + ((ln & 15) * 32 + (ln & 16)) : dst;
        const uint8_t* src1 = src0 + (isH ? 512 : 256);
        uint32_t v[32];
#pragma unroll
        for (int i = 0; i < 8; i++) {
          const uint4 u = *(const uint4*)(((i & 1) ? src1 : src0) + (i >> 1) * 1024);
          v[4 * i] = u.x; v[4 * i + 1] = u.y; v[4 * i + 2] = u.z; v[4 * i + 3] = u.w;
        }
        if (isH) mbar_wait(BAR(B_XT), 0);
        const float f0 = __uint_as_float(v[0] << 16) + ((isH && ln == 0) ? *(const float*)(smem + OFF_D + 4 * c) : 0.f);
        const int e = norm_exp(v, f0);
        norm_cvt(v, f0, e);
        if (isH) mbar_wait(BAR(B_SFREE), 0);
        else if (ln == 0) smem[OFF_EX + c] = e;
        e1 = e;
#pragma unroll
        for (int i = 0; i < 8; i++)
          *(uint4*)(dst + (i >> 1) * 1024 + (i & 1) * 256) = make_uint4(v[4 * i], v[4 * i + 1], v[4 * i + 2], v[4 * i + 3]);
        if (n < 2 && elect_one()) {
          if (n == 0) mbar_expect(sbar, 4096);
          tma3d(sb + OFF_STG + 2048 * c, &P.tmQ, 16 * cl, 64 * rank, 2 * c, sbar);
        }
      }
      if (n >= 2) {
        fence_async();
        __syncwarp();
        if (lane == 0) { mbar_arrive(BAR(isH ? B_H : B_XT)); STAMP(3, (isH ? 17 : 13) + hw); }
      }
    }
#define SLOT(tab, kb) (sb + ((uint32_t)((tab) >> (4 * (kb))) & 15) * 16384)
#define KT(kb) (!OLOC ? (kb) : (kb) == 0 ? hq : (kb) == hq ? 0 : (kb))
#define LOAD_B(kb) tma4d(SLOT(SLOT_B, kb), &P.tmWo, 0, ((kb) >> 3) * 32, 2 * (KT(kb) & 7), 4 * cb + 2 * rank, BAR(B_FULL2 + (kb)))
#define LOAD_A(kb) bulk_ld_mc(SLOT(SLOT_A, kb) + rank * 8192, P.o + rb * OBLK + KT(kb) * 1024 + rank * 512, 8192, BAR(B_FULL2 + (kb)))
    asm volatile("setmaxnreg.inc.sync.aligned.u32 %0;" ::"n"(504 - 2 * RC));
    {
    int tid;
    asm volatile("mov.u32 %0, %%tid.x;" : "=r"(tid));
    const int lane = tid & 31, g = lane >> 2, q = lane & 3;
    const unsigned epoch = *(volatile unsigned*)(smem + OFF_EPOCH);
    const uint32_t tag = ~epoch & 1;
    const int pi = hw < 2 ? 64 * mb - 288 + tid : 512 + 8 * (mb & 1) + (mb & 6) + (lane & 1);
    const float* psrc = P.part + hp * 8 * 2176 + 4 * pi;
    uint4 f[8];
    {
      const uint32_t s16 = (sb & 0x3FFFF) >> 4;
      const int t = tid & 127, c = 2 + (warp & 1) + 2 * (warp & 2);
      const uint4* hp4 = (const uint4*)(P.h + (16 * cl + 8 * rank + c) * 2048) + ((lane & 15) * 2 + (lane >> 4));
      uint32_t v[32];
#pragma unroll
      for (int i = 0; i < 8; i++) { const uint4 u = ld_na4(hp4 + i * 32); v[4 * i] = u.x; v[4 * i + 1] = u.y; v[4 * i + 2] = u.z; v[4 * i + 3] = u.w; }
      float kva[36];
#pragma unroll
      for (int mt = 0; mt < 2; mt++) {
        mbar_wait(BAR(B_PKRDY + mt), 0);
        wg_fence();
#pragma unroll
        for (int ks = 0; ks < 8; ks++) {
          const uint32_t o = (ks >> 2) * 1024 + mt * 512 + (ks & 3) * 128, vb = (2 * STAGE_BYTES >> 4) + o;
          wgmma_ss_n72<1, 1>(kva, dsc(s16 + o + (1 << 16), SW128), dsc(s16 + vb + (((OFF_ONES >> 4) - vb) << 16), SW128), (mt | ks) != 0);
        }
        wg_commit();
        if (mt == 0 && hw < 0) {
          mbar_wait(BAR(B_G1DONE), 0);
          if (elect_one()) {
#pragma unroll
            for (int kb = 0; kb < BEARLY; kb++) { mbar_expect(BAR(B_FULL2 + kb), 16384); LOAD_B(kb); }
          }
        }
      }
      float* pdst = P.part + (hp * 8 + mb) * 2176 + t * 4;
      float* zdst = P.part + (hp * 8 + mb) * 2176 + 2048 + (t >> 1);
      asm volatile("" : "+l"(pdst), "+l"(zdst));
      wg_wait<0>();
      keep(kva);
      if (hw < 1) {
#pragma unroll
        for (int c = 0; c < 4; c++) st_tag4(pdst + c * 512, kva[4 * c], kva[4 * c + 1], kva[4 * c + 2], kva[4 * c + 3], tag);
      } else {
#pragma unroll
        for (int c = 4; c < 8; c++) st_tag4(pdst + (c - 4) * 512, kva[4 * c], kva[4 * c + 1], kva[4 * c + 2], kva[4 * c + 3], tag);
      }
      const float z2 = __shfl_down_sync(~0u, kva[32], 4), z3 = __shfl_down_sync(~0u, kva[34], 4);
      if (!(lane & 7)) st_tag4(zdst, kva[32], kva[34], z2, z3, tag);
      if (lane == 0) mbar_arrive(BAR(B_PKFREE));
      const uint32_t cst = clock();
      if (hw == 0 && lane == 0) STAMP(3, 24);
      const float f0 = __uint_as_float(v[0] << 16) + (lane == 0 ? *(const float*)(smem + OFF_D + 4 * c) : 0.f);
      const int e = norm_exp(v, f0);
      norm_cvt(v, f0, e);
      if (hw >= 0) {
        while (__any_sync(~0u, (uint32_t)clock() - cst < PD1)) __nanosleep(20);
        if (hw == 0 && lane == 0) STAMP(3, 20);
#pragma unroll
        for (int p = 0; p < 8; p++) f[p] = ld_rlx4(psrc + p * 2176);
      }
      uint8_t* dst = smem + OFF_H + 16384 + (warp & 3) * 4096 + (lane >> 4) * 512 + (lane & 15) * 16;
#pragma unroll
      for (int i = 0; i < 8; i++)
        *(uint4*)(dst + (i >> 1) * 1024 + (i & 1) * 256) = make_uint4(v[4 * i], v[4 * i + 1], v[4 * i + 2], v[4 * i + 3]);
      if (lane < 4) {
        const int cc = c - (lane & 2);
        st_async(mapa(sb + OFF_SCALE + (8 * rank + cc) * 4, lane & 1), min(max(((lane & 2) ? e1 : e) + smem[OFF_EX + cc] - 124, 1), 254) << 23, mapa(BAR(B_Y), lane & 1));
      }
    }
#define H2_READY() do { fence_async(); __syncwarp(); if (lane == 0) mbar_arrive(BAR(B_H2)); } while (0)
    if (warp == 8) {
      H2_READY();
      mbar_wait(BAR(B_PKFREE), 0);
      {
        const uint32_t c0 = clock();
#pragma unroll 1
        for (int i = 0; i < 2 * NPRE - 2 * BEARLY; i++) {
          const int kb = (i >> 1) + BEARLY;
          while (__any_sync(~0u, (uint32_t)clock() - c0 < i * BPACE)) __nanosleep(32);
          if (elect_one()) {
            if (!(i & 1)) mbar_expect(BAR(B_FULL2 + kb), 16384);
            tma4d(SLOT(SLOT_B, kb) + (i & 1) * 8192, &P.tmWo1, 0, 0, 2 * KT(kb), 4 * cb + 2 * rank + (i & 1), BAR(B_FULL2 + kb));
            if (i == 0) mbar_expect(BAR(B_Q), 8192);
            if (i < 4) tma3d(sb + OFF_SPARE + 2048 * i, &P.tmQ, 16 * cl, 64 * rank + 32 * (i >> 1), 2 * ((i + 6) & 7), BAR(B_Q));
          }
        }
      }
      if (elect_one()) { MAP_PF(tmOA); MAP_PF(tmOB); }
      if (lane == 0) STAMP(2, 2);
      if (OLOC) {
        if (elect_one()) mbar_expect(BAR(B_FULL2), 16384);
        mbar_wait(BAR(B_OLOC), 0);
        asm volatile("fence.acquire.cluster;\nfence.proxy.async.global;" ::: "memory");
        if (elect_one()) LOAD_A(0);
      }
      mbar_wait(BAR(B_AFREE), 0);
      if (elect_one()) mbar_expect(BAR(B_FULL2 + OLOC), 16384);
      {
        const uint32_t dst = SLOT(SLOT_A, OLOC) + rank * 8192;
        const uint4* src = P.o + rb * OBLK + KT(OLOC) * 1024 + rank * 512;
        poll_ge(OCNT(rb, 0), 16 * (epoch + 1));
        asm volatile("fence.proxy.async.global;" ::: "memory");
        if (lane == 0) STAMP(2, 3);
        if (elect_one()) bulk_ld_mc(dst, src, 8192, BAR(B_FULL2 + OLOC));
        if (lane == 0) STAMP(3, 23);
      }
#pragma unroll 1
      for (int kb = 1 + OLOC; kb < NPRE; kb++) {
        mbar_wait(BAR(kb < 4 ? B_AFREE + kb - 1 : B_CONS2), 0);
        if (elect_one()) { mbar_expect(BAR(B_FULL2 + kb), 16384); LOAD_A(kb); }
      }
#pragma unroll 1
      for (int kb = NPRE; kb < 16; kb++) {
        mbar_wait(BAR(B_CONS2 + kb - 5), 0);
        if (kb == 8) mbar_wait(BAR(B_O1RDY), 0);
        if (elect_one()) { mbar_expect(BAR(B_FULL2 + kb), 32768); LOAD_A(kb); LOAD_B(kb); }
      }
      if (lane == 0) { EPOCH = epoch + 1; STAMP(2, 5); }
    } else {
      {
#pragma unroll 1
        for (int n = 0; __any_sync(~0u, stale8(f, tag) & 1); n++) {
#pragma unroll
          for (int p = 0; p < 8; p++) ld_stale4(f[p], psrc + p * 2176, tag);
          if (n > SPIN_LIMIT) __trap();
        }
        float s0 = 0.f, s1 = 0.f, s2 = 0.f, s3 = 0.f;
#pragma unroll
        for (int p = 0; p < 8; p++) { s0 += __uint_as_float(f[p].x); s1 += __uint_as_float(f[p].y); s2 += __uint_as_float(f[p].z); s3 += __uint_as_float(f[p].w); }
        if (hw < 2 || lane < 2) st_tag4(P.kv + hp * 2176 + (4 * pi), s0, s1, s2, s3, tag);
      }
      const uint32_t cs2 = clock();
      if (lane == 0 && hw == 0) STAMP(3, 8);
      H2_READY();
      if (hw == 2) {
        unsigned* cnt = OCNT(2 * mb + lane, 0);
#pragma unroll 1
        for (int hh = 0; hh < 2; hh++) {
          mbar_wait(BAR(hh ? B_ODONE1 : B_ODONE), 0);
          if (lane < 2) asm volatile("red.release.gpu.global.add.u32 [%0], 1;" ::"l"(cnt) : "memory");
          if (OLOC && hh == 0 && lane < 2) mbar_arrive_cl(BAR(B_OLOC), lane);
          cnt += 32;
          if (lane == 0) STAMP(3, hh ? 6 : 7);
        }
        poll_ge(OCNT(rb, 1), 16 * (epoch + 1));
        asm volatile("fence.proxy.async.global;" ::: "memory");
        if (lane == 0) { mbar_arrive(BAR(B_O1RDY)); STAMP(2, 4); }
        __syncwarp();
      } else {
        const int t = tid - 288;
        const float* src = P.kv + hp * 2176 + 4 * (t + 32 * hw);
        const float* zsrc = P.kv + hp * 2176 + (2048 + (t & 48) + 2 * (lane & 6));
        mbar_wait(BAR(B_PKFREE), 0);
        while (__any_sync(~0u, (uint32_t)clock() - cs2 < PD2)) __nanosleep(20);
        uint4 zp = ld_rlx4(zsrc);
#pragma unroll
        for (int p = 0; p < 8; p++) f[p] = ld_rlx4(src + 4 * ((p & 3) * 128 + (p >> 2) * 32));
        if (!opaque_true()) __trap();
#pragma unroll 1
        for (int n = 0; __any_sync(~0u, (stale8(f, tag) | (zp.x ^ tag)) & 1); n++) {
          ld_stale4(zp, zsrc, tag);
#pragma unroll
          for (int p = 0; p < 8; p++) ld_stale4(f[p], src + 4 * ((p & 3) * 128 + (p >> 2) * 32), tag);
          if (n > SPIN_LIMIT) __trap();
        }
#define PK2U(a, b) pk2(__uint_as_float(a), __uint_as_float(b))
        const uint32_t zf = (lane & 1) ? ((lane & 8) ? zp.w : zp.z) : ((lane & 8) ? zp.y : zp.x);
        const uint32_t zz = PK2U(zf, zf);
        *(uint4*)(smem + OFF_KVB + hw * 2560 + 2048 + lane * 16) = make_uint4(zz, zz, zz, zz);
#pragma unroll
        for (int hh = 0; hh < 2; hh++) {
          const uint4* ff = &f[4 * hh];
          uint8_t* dst = smem + OFF_KVB + hw * 2560 + q * 512 + (16 * hh + g) * 16;
          *(uint4*)dst = make_uint4(PK2U(ff[0].x, ff[0].y), PK2U(ff[1].x, ff[1].y), PK2U(ff[2].x, ff[2].y), PK2U(ff[3].x, ff[3].y));
          *(uint4*)(dst + 128) = make_uint4(PK2U(ff[0].z, ff[0].w), PK2U(ff[1].z, ff[1].w), PK2U(ff[2].z, ff[2].w), PK2U(ff[3].z, ff[3].w));
        }
        fence_async();
        __syncwarp();
        if (lane == 0) { mbar_arrive(BAR(hw ? B_KV1 : B_KV)); if (hw == 0) STAMP(3, 9); }
      }
#define QBUF(ci) (sb + 2048 * (ci) + ((ci) < 6 ? OFF_STG : (ci) < 10 ? OFF_SPARE - 6 * 2048 : OFF_F2F - 10 * 2048))
      mbar_wait(BAR(B_Y), 0);
      if (elect_one()) {
        mbar_expect(sbar + 8, 4096);
#pragma unroll 1
        for (int ci = hw ? hw + 9 : 12; ci < 16; ci += 3) tma3d(QBUF(ci), &P.tmQ, 16 * cl, 64 * rank + 32, 2 * (ci & 7), sbar + 8);
      }
      mbar_wait(BAR(B_Q), 0);
      mbar_wait(sbar, hw == 0);
      {
        const uint2 f0 = *(const uint2*)(smem + OFF_SCALE + 8 * q), f1 = *(const uint2*)(smem + OFF_SCALE + 32 + 8 * q);
        const uint32_t sc0 = __byte_perm(f0.x, f0.y, 0x7632), sc1 = __byte_perm(f1.x, f1.y, 0x7632);
        const uint32_t yl = sb + OFF_XT + (lane & 7) * XT_STRIDE + (lane >> 3) * 16;
#pragma unroll 1
        for (int ci = hw; ci < 16; ci += 3) {
          const uint32_t qb = QBUF(ci);
          if (ci >= 10) mbar_wait(sbar + 8, 1);
          uint32_t yy[4][4], qq[4][4];
          const uint32_t qa = qb + lane * 32 + ((lane & 4) << 2);
#pragma unroll
          for (int u = 0; u < 4; u++) {
            ldsm4t(yy[u], yl + (u & 1) * 2048 + (2 * ci + (u >> 1)) * 64);
            ldsm4(qq[u], (qa ^ ((u & 1) * 16)) + (u >> 1) * 1024);
          }
          if (!opaque_true()) __trap();
#pragma unroll
          for (int u = 0; u < 4; u++) {
#pragma unroll
            for (int m = 0; m < 4; m++) {
              const float2 f = __half22float2(*(const __half2*)&yy[u][m]);
              qq[u][m] = hmul(qq[u][m], hmul(pk2(f.x, f.y), (u & 1) ? sc1 : sc0));
            }
            stsm4((qa ^ ((u & 1) * 16)) + (u >> 1) * 1024, qq[u][0], qq[u][1], qq[u][2], qq[u][3]);
          }
          fence_async();
          __syncwarp();
          if (elect_one()) tma3d_st(&P.tmOA, qb, 16 * cl, 64 * rank + 32 * (ci >> 3), 2 * (ci & 7));
        }
        asm volatile("cp.async.bulk.commit_group;\ncp.async.bulk.wait_group.read 0;" ::: "memory");
      }
      if (lane == 0) STAMP(3, 10 + hw);
    }
    }
  }
}

typedef CUresult (*EncodeFn)(CUtensorMap*, CUtensorMapDataType, cuuint32_t, void*, const cuuint64_t*, const cuuint64_t*,
                             const cuuint32_t*, const cuuint32_t*, CUtensorMapInterleave, CUtensorMapSwizzle,
                             CUtensorMapL2promotion, CUtensorMapFloatOOBfill);

static void enc(EncodeFn fn, CUtensorMap* m, const void* p, int rank, const cuuint64_t* dims, const cuuint64_t* strides,
                const cuuint32_t* box, CUtensorMapSwizzle swz, CUtensorMapL2promotion promo) {
  cuuint32_t es[4] = {1, 1, 1, 1};
  fn(m, CU_TENSOR_MAP_DATA_TYPE_BFLOAT16, rank, (void*)p, dims, strides, box, es, CU_TENSOR_MAP_INTERLEAVE_NONE, swz, promo,
     CU_TENSOR_MAP_FLOAT_OOB_FILL_NONE);
}

extern "C" void kernel_launch(void* const* d_in, const int* in_sizes, int n_in, void* d_out, int out_size) {
  void* fp = nullptr;
  cudaDriverEntryPointQueryResult qr;
  cudaGetDriverEntryPoint("cuTensorMapEncodeTiled", &fp, cudaEnableDefault, &qr);
  EncodeFn fn = (EncodeFn)fp;
  Params P;
  P.shift_k = (const __nv_bfloat16*)d_in[3]; P.h = (const __nv_bfloat16*)d_in[4]; P.D = (const __nv_bfloat16*)d_in[5];
  P.q = (const __nv_bfloat16*)d_in[0];
  cudaGetSymbolAddress((void**)&P.part, g_part); cudaGetSymbolAddress((void**)&P.kv, g_kv); cudaGetSymbolAddress((void**)&P.o, g_o);
  cudaGetSymbolAddress((void**)&P.thr, c_thr); cudaGetSymbolAddress((void**)&P.img, c_img);
  P.x = (const __nv_bfloat16*)d_in[6]; P.w = (const __nv_bfloat16*)d_in[7]; P.wo = (const __nv_bfloat16*)d_in[8];
  const CUtensorMapSwizzle S128 = CU_TENSOR_MAP_SWIZZLE_128B, S32 = CU_TENSOR_MAP_SWIZZLE_32B;
  const CUtensorMapL2promotion P0 = CU_TENSOR_MAP_L2_PROMOTION_NONE, P128 = CU_TENSOR_MAP_L2_PROMOTION_L2_128B;
  { cuuint64_t d[2] = {1024, 2048}, s[1] = {2048}; cuuint32_t b[2] = {64, 128}; enc(fn, &P.tmX, d_in[6], 2, d, s, b, S128, P128); }
  { cuuint64_t d[2] = {1024, 2048}, s[1] = {2048}; cuuint32_t b[2] = {64, 64}; enc(fn, &P.tmX0, d_in[6], 2, d, s, b, S128, P128); }
  { cuuint64_t d[3] = {1024, 1024, 3}, s[2] = {6144, 2048}; cuuint32_t b[3] = {64, 64, 3}; enc(fn, &P.tmW, d_in[7], 3, d, s, b, S128, P128); }
  { cuuint64_t d[4] = {64, 64, 16, 16}, s[3] = {2048, 131072, 128}; cuuint32_t b[4] = {64, 32, 2, 2}; enc(fn, &P.tmWo, d_in[8], 4, d, s, b, S128, P128); }
  { cuuint64_t d[4] = {64, 64, 16, 16}, s[3] = {2048, 131072, 128}; cuuint32_t b[4] = {64, 32, 2, 1}; enc(fn, &P.tmWo1, d_in[8], 4, d, s, b, S128, P128); }
  { cuuint64_t d[2] = {1024, 2048}, s[1] = {2048}; cuuint32_t b[2] = {16, 72}; enc(fn, &P.tmK, d_in[1], 2, d, s, b, S32, P128); }
  { cuuint64_t d[2] = {1024, 2048}, s[1] = {2048}; cuuint32_t b[2] = {16, 64}; enc(fn, &P.tmV, d_in[2], 2, d, s, b, S32, P128); }
  { cuuint64_t d[3] = {1024, 128, 16}, s[2] = {32768, 2048}; cuuint32_t b[3] = {16, 32, 2}; enc(fn, &P.tmQ, d_in[0], 3, d, s, b, S32, P128); }
  { cuuint64_t d[3] = {1024, 128, 16}, s[2] = {65536, 4096}; cuuint32_t b[3] = {16, 32, 2}; enc(fn, &P.tmOA, d_out, 3, d, s, b, S32, P0); }
  { cuuint64_t d[2] = {2048, 2048}, s[1] = {4096}; cuuint32_t b[2] = {64, 16}; enc(fn, &P.tmOB, d_out, 2, d, s, b, S128, P0); }
  cudaFuncSetAttribute(fused_kernel, cudaFuncAttributeMaxDynamicSharedMemorySize, SMEM_TOTAL);
  fused_kernel<<<128, 384, SMEM_TOTAL>>>(P);
}
```

```cpp
#include <cuda_runtime.h>
#include <cuda_bf16.h>
#include <cuda_fp16.h>
#include <cuda.h>
#include <stdint.h>

template<int TA, int TB, int SA=1> __device__ __forceinline__ void wgmma_ss_n192(float (&d)[96], uint64_t da, uint64_t db, int scale_d) {
  asm volatile("{\n.reg .pred p;\nsetp.ne.b32 p, %98, 0;\n"
    "wgmma.mma_async.sync.aligned.m64n192k16.f32.bf16.bf16 {%0, %1, %2, %3, %4, %5, %6, %7, %8, %9, %10, %11, %12, %13, %14, %15, %16, %17, %18, %19, %20, %21, %22, %23, %24, %25, %26, %27, %28, %29, %30, %31, %32, %33, %34, %35, %36, %37, %38, %39, %40, %41, %42, %43, %44, %45, %46, %47, %48, %49, %50, %51, %52, %53, %54, %55, %56, %57, %58, %59, %60, %61, %62, %63, %64, %65, %66, %67, %68, %69, %70, %71, %72, %73, %74, %75, %76, %77, %78, %79, %80, %81, %82, %83, %84, %85, %86, %87, %88, %89, %90, %91, %92, %93, %94, %95}, %96, %97, p, %101, 1, %99, %100;\n}\n"
    : "+f"(d[0]), "+f"(d[1]), "+f"(d[2]), "+f"(d[3]), "+f"(d[4]), "+f"(d[5]), "+f"(d[6]), "+f"(d[7]), "+f"(d[8]), "+f"(d[9]), "+f"(d[10]), "+f"(d[11]), "+f"(d[12]), "+f"(d[13]), "+f"(d[14]), "+f"(d[15]), "+f"(d[16]), "+f"(d[17]), "+f"(d[18]), "+f"(d[19]), "+f"(d[20]), "+f"(d[21]), "+f"(d[22]), "+f"(d[23]), "+f"(d[24]), "+f"(d[25]), "+f"(d[26]), "+f"(d[27]), "+f"(d[28]), "+f"(d[29]), "+f"(d[30]), "+f"(d[31]), "+f"(d[32]), "+f"(d[33]), "+f"(d[34]), "+f"(d[35]), "+f"(d[36]), "+f"(d[37]), "+f"(d[38]), "+f"(d[39]), "+f"(d[40]), "+f"(d[41]), "+f"(d[42]), "+f"(d[43]), "+f"(d[44]), "+f"(d[45]), "+f"(d[46]), "+f"(d[47]), "+f"(d[48]), "+f"(d[49]), "+f"(d[50]), "+f"(d[51]), "+f"(d[52]), "+f"(d[53]), "+f"(d[54]), "+f"(d[55]), "+f"(d[56]), "+f"(d[57]), "+f"(d[58]), "+f"(d[59]), "+f"(d[60]), "+f"(d[61]), "+f"(d[62]), "+f"(d[63]), "+f"(d[64]), "+f"(d[65]), "+f"(d[66]), "+f"(d[67]), "+f"(d[68]), "+f"(d[69]), "+f"(d[70]), "+f"(d[71]), "+f"(d[72]), "+f"(d[73]), "+f"(d[74]), "+f"(d[75]), "+f"(d[76]), "+f"(d[77]), "+f"(d[78]), "+f"(d[79]), "+f"(d[80]), "+f"(d[81]), "+f"(d[82]), "+f"(d[83]), "+f"(d[84]), "+f"(d[85]), "+f"(d[86]), "+f"(d[87]), "+f"(d[88]), "+f"(d[89]), "+f"(d[90]), "+f"(d[91]), "+f"(d[92]), "+f"(d[93]), "+f"(d[94]), "+f"(d[95])
    : "l"(da), "l"(db), "r"(scale_d), "n"(TA), "n"(TB), "n"(SA));
}
template<int TA, int TB, int SA=1> __device__ __forceinline__ void wgmma_ss_n128(float (&d)[64], uint64_t da, uint64_t db, int scale_d) {
  asm volatile("{\n.reg .pred p;\nsetp.ne.b32 p, %66, 0;\n"
    "wgmma.mma_async.sync.aligned.m64n128k16.f32.bf16.bf16 {%0, %1, %2, %3, %4, %5, %6, %7, %8, %9, %10, %11, %12, %13, %14, %15, %16, %17, %18, %19, %20, %21, %22, %23, %24, %25, %26, %27, %28, %29, %30, %31, %32, %33, %34, %35, %36, %37, %38, %39, %40, %41, %42, %43, %44, %45, %46, %47, %48, %49, %50, %51, %52, %53, %54, %55, %56, %57, %58, %59, %60, %61, %62, %63}, %64, %65, p, %69, 1, %67, %68;\n}\n"
    : "+f"(d[0]), "+f"(d[1]), "+f"(d[2]), "+f"(d[3]), "+f"(d[4]), "+f"(d[5]), "+f"(d[6]), "+f"(d[7]), "+f"(d[8]), "+f"(d[9]), "+f"(d[10]), "+f"(d[11]), "+f"(d[12]), "+f"(d[13]), "+f"(d[14]), "+f"(d[15]), "+f"(d[16]), "+f"(d[17]), "+f"(d[18]), "+f"(d[19]), "+f"(d[20]), "+f"(d[21]), "+f"(d[22]), "+f"(d[23]), "+f"(d[24]), "+f"(d[25]), "+f"(d[26]), "+f"(d[27]), "+f"(d[28]), "+f"(d[29]), "+f"(d[30]), "+f"(d[31]), "+f"(d[32]), "+f"(d[33]), "+f"(d[34]), "+f"(d[35]), "+f"(d[36]), "+f"(d[37]), "+f"(d[38]), "+f"(d[39]), "+f"(d[40]), "+f"(d[41]), "+f"(d[42]), "+f"(d[43]), "+f"(d[44]), "+f"(d[45]), "+f"(d[46]), "+f"(d[47]), "+f"(d[48]), "+f"(d[49]), "+f"(d[50]), "+f"(d[51]), "+f"(d[52]), "+f"(d[53]), "+f"(d[54]), "+f"(d[55]), "+f"(d[56]), "+f"(d[57]), "+f"(d[58]), "+f"(d[59]), "+f"(d[60]), "+f"(d[61]), "+f"(d[62]), "+f"(d[63])
    : "l"(da), "l"(db), "r"(scale_d), "n"(TA), "n"(TB), "n"(SA));
}
template<int TA, int TB, int SA=1> __device__ __forceinline__ void wgmma_ss_n72(float (&d)[36], uint64_t da, uint64_t db, int scale_d) {
  asm volatile("{\n.reg .pred p;\nsetp.ne.b32 p, %38, 0;\n"
    "wgmma.mma_async.sync.aligned.m64n72k16.f32.bf16.bf16 {%0, %1, %2, %3, %4, %5, %6, %7, %8, %9, %10, %11, %12, %13, %14, %15, %16, %17, %18, %19, %20, %21, %22, %23, %24, %25, %26, %27, %28, %29, %30, %31, %32, %33, %34, %35}, %36, %37, p, %41, 1, %39, %40;\n}\n"
    : "+f"(d[0]), "+f"(d[1]), "+f"(d[2]), "+f"(d[3]), "+f"(d[4]), "+f"(d[5]), "+f"(d[6]), "+f"(d[7]), "+f"(d[8]), "+f"(d[9]), "+f"(d[10]), "+f"(d[11]), "+f"(d[12]), "+f"(d[13]), "+f"(d[14]), "+f"(d[15]), "+f"(d[16]), "+f"(d[17]), "+f"(d[18]), "+f"(d[19]), "+f"(d[20]), "+f"(d[21]), "+f"(d[22]), "+f"(d[23]), "+f"(d[24]), "+f"(d[25]), "+f"(d[26]), "+f"(d[27]), "+f"(d[28]), "+f"(d[29]), "+f"(d[30]), "+f"(d[31]), "+f"(d[32]), "+f"(d[33]), "+f"(d[34]), "+f"(d[35])
    : "l"(da), "l"(db), "r"(scale_d), "n"(TA), "n"(TB), "n"(SA));
}
template<int TB, int SA=1> __device__ __forceinline__ void wgmma_rs_n40(float (&d)[20], uint32_t a0, uint32_t a1, uint32_t a2, uint32_t a3, uint64_t db, int scale_d) {
  asm volatile("{\n.reg .pred p;\nsetp.ne.b32 p, %25, 0;\n"
    "wgmma.mma_async.sync.aligned.m64n40k16.f32.bf16.bf16 {%0, %1, %2, %3, %4, %5, %6, %7, %8, %9, %10, %11, %12, %13, %14, %15, %16, %17, %18, %19}, {%20, %21, %22, %23}, %24, p, %27, 1, %26;\n}\n"
    : "+f"(d[0]), "+f"(d[1]), "+f"(d[2]), "+f"(d[3]), "+f"(d[4]), "+f"(d[5]), "+f"(d[6]), "+f"(d[7]), "+f"(d[8]), "+f"(d[9]), "+f"(d[10]), "+f"(d[11]), "+f"(d[12]), "+f"(d[13]), "+f"(d[14]), "+f"(d[15]), "+f"(d[16]), "+f"(d[17]), "+f"(d[18]), "+f"(d[19])
    : "r"(a0), "r"(a1), "r"(a2), "r"(a3), "l"(db), "r"(scale_d), "n"(TB), "n"(SA));
}
template<int TB> __device__ __forceinline__ void wgmma_hrs_n64(uint32_t (&d)[16], uint32_t a0, uint32_t a1, uint32_t a2, uint32_t a3, uint64_t db, int scale_d) {
  asm volatile("{\n.reg .pred p;\nsetp.ne.b32 p, %21, 0;\n"
    "wgmma.mma_async.sync.aligned.m64n64k16.f16.f16.f16 {%0, %1, %2, %3, %4, %5, %6, %7, %8, %9, %10, %11, %12, %13, %14, %15}, {%16, %17, %18, %19}, %20, p, 1, 1, %22;\n}\n"
    : "+r"(d[0]), "+r"(d[1]), "+r"(d[2]), "+r"(d[3]), "+r"(d[4]), "+r"(d[5]), "+r"(d[6]), "+r"(d[7]), "+r"(d[8]), "+r"(d[9]), "+r"(d[10]), "+r"(d[11]), "+r"(d[12]), "+r"(d[13]), "+r"(d[14]), "+r"(d[15])
    : "r"(a0), "r"(a1), "r"(a2), "r"(a3), "l"(db), "r"(scale_d), "n"(TB));
}
template<int TB> __device__ __forceinline__ void wgmma_hrs_n32(uint32_t (&d)[8], uint32_t a0, uint32_t a1, uint32_t a2, uint32_t a3, uint64_t db, int scale_d) {
  asm volatile("{\n.reg .pred p;\nsetp.ne.b32 p, %13, 0;\n"
    "wgmma.mma_async.sync.aligned.m64n32k16.f16.f16.f16 {%0, %1, %2, %3, %4, %5, %6, %7}, {%8, %9, %10, %11}, %12, p, 1, 1, %14;\n}\n"
    : "+r"(d[0]), "+r"(d[1]), "+r"(d[2]), "+r"(d[3]), "+r"(d[4]), "+r"(d[5]), "+r"(d[6]), "+r"(d[7])
    : "r"(a0), "r"(a1), "r"(a2), "r"(a3), "l"(db), "r"(scale_d), "n"(TB));
}

__device__ __align__(128) const uint32_t c_thr[1536] = {
  0x33fb33ff,0xa49c9de4,0x33273352,0xaf2cae76,0x33e233f1,0xa96ca7bd,0x32c432f7,0xb045afdd,0x33b733cf,0xac3eaaf7,0x3250328c,0xb0eab099,
  0x3378339a,0xadbcacff,0x31cd3211,0xb182b137,0x33d033fb,0xaadea46a,0x299e2d17,0xb3e0b396,0x32fb337a,0xafd2adb1,0xa78b1f76,0xb3f2b3ff,
  0x318b3254,0xb1c5b0e5,0xae6bac32,0xb354b3b8,0x2f4230a3,0xb321b285,0xb133b040,0xb215b2c7,0x337c33f2,0xada5a759,0xb179afc8,0xb1d6b2fe,
  0x31463293,0xb204b08e,0xb394b2ba,0xad23b055,0x2b402f4e,0xb3cbb31e,0xb3e4b3f9,0x293ba533,0xac269c52,0xb3bab400,0xb258b357,0x30e02e5f,
  0x330133e5,0xafbda922,0xb3f3b3c9,0x2727ab59,0x2deb314a,0xb36fb200,0xb194b32f,0x31bc2f0a,0xacdb2084,0xb39fb3ff,0xa565aea4,0x33f93347,
  0xb2b6b0db,0xb05ab25c,0x30892c1a,0x329733bc,0x326033d4,0xb0d6aa94,0xb00ab29b,0x32e83084,0x20e82f64,0xb3feb318,0x2d8da597,0x338133f8,
  0xb1fcae48,0xb14fb35c,0x339031b8,0x2d3a3199,0xb3e6b3ae,0x2909ac7b,0x32d133f4,0xb030a6f5,0x319d33bf,0xb1b3ac02,0x2e3ca874,0x335e33ec,
  0xacc32b89,0xb3a3b3c6,0x33f83276,0x25c930b7,0xb3dcb1f8,0xaa01b154,0x30653335,0xb2b0aef4,0xb107b383,0x32392d81,0xafa6214d,0xb307b3fe,
  0x30bc33a5,0xb273acb7,0x33c5311b,0x2ba23229,0xb0cc94b6,0xb267b400,0x30153360,0xb2e1ae31,0xb385b3ab,0x2d76ac93,0xb166a691,0xb1e7b3f5,
  0x22deb06a,0x33fd32ac,0xb337b3da,0x2ee8aa19,0x2f853387,0xb310ad6a,0x322d33fe,0xb1162216,0xb2a9abd3,0xb06fb3c2,0xb07428a6,0xb2a5b3ea,
  0xb111b3e9,0x323128be,0xb30db3c3,0x2f90abba,0x31aa227a,0x31a633fd,0x2e25ad5e,0x33633389,0x2d6a3365,0xb387ae1a,0xa21631aa,0xb3feb1a6,
  0xb3c2af85,0xabd3b310,0xb3eab22d,0x28a6b116,0xa8beb2a9,0x33e9306f,0x2bbab074,0x33c332a5,0x33fd3111,0x227a3231,0x3389330d,0xad5e2f90,
  0x2a63333f,0xb3d7aec6,0xb2a2a1b1,0xb07ab3fe,0xb3f7b158,0x25fbb1f4,0xacb7b38b,0x33a52d52,0x2e0eb025,0x336832d8,0x340030bc,0x14b63273,
  0x323533c0,0xb10c2beb,0xac9330cc,0xb3abb267,0x23433316,0xb3fdaf6f,0xb38eb225,0x2d46b11f,0xb342b29e,0x2ebbb07f,0x31e3aa7c,0x316b33d6,
  0x3264a6c3,0x30d133f5,0x2c0233ac,0xb3bfac87,0x28f0336a,0xb3e7ae02,0xb3c6b19d,0x2b89b1b3,0xa59732e8,0xb3f8b00a,0xaccfb3ed,0x33a1285b,
  0xb1b8b381,0x3199ad8d,0x336c31df,0xadf73170,0x33f42d3a,0x26f53390,0xb30423a7,0xafb2b3fc,0xb05f3030,0xb2b3b2d1,0x29e8b27a,0x33dd30b2,
  0xab5932b6,0xb3c9b05a,0x30adb089,0x327e3297,0xaf0ab3f3,0x332fa727,0x240633b0,0xb3fcac6f,0x33473194,0xaea431bc,0xb174b359,0x31daae54,
  0xb3bca565,0xac1ab3f9,0x33ee2f59,0xa842331b,0xaddf3281,0xb371b0a8,0x34002b40,0x1c5233cb,0xa759b3ef,0x33f22829,0xb2fe2c26,0xafc8b3ba,
  0x308e337c,0xb2932da5,0x3055b179,0x32ba31d6,0xb31eb146,0x2f4eb204,0xa5333394,0xb3f9ad23,0xaff33249,0xb2f1b0f3,0x30e532fb,0xb2542fd2,
  0x2b28b373,0x33cc2dd4,0xb285b18b,0x30a3b1c5,0x246a33fa,0xb3fba500,0x33962f42,0xad173321,0xadb1b3d0,0x337aaade,0xb3ffa99e,0x1f76b3e0,
  0xb0ee320d,0xb24db13c,0xac4b3398,0xb3b5ad0b,0x304ab289,0x32c1309e,0x2985b3ce,0x33e12b0f,0xaf3732f4,0xb324afe8,0xa4ce33f0,0xb3faa7ef,
  0x2dc8b34f,0x33762e82,0x9de4b3ff,0x33ff1ead,0xb1c931cd,0xb186b182,0xb3762e82,0xadc8b34f,0x324db13c,0x30ee320d,0x33b5ad0b,0x2c4b3398,
  0xb2c1309e,0xb04ab289,0xb3e12b0f,0xa985b3ce,0x3324afe8,0x2f3732f4,0x33faa7ef,0x24ce33f0,0xb285318b,0xb0a3b1c5,0xb2c7ae6b,0x3040b354,
  0x3396af42,0x2d173321,0x31413133,0xb2093215,0xb3ff299e,0x9f76b3e0,0xae8db2bd,0x334cb050,0x33b8278b,0xac3233f2,0x281033b3,0xb3ef2c57,
  0xb31e3146,0xaf4eb204,0xa533b394,0x33f9ad23,0x3400ab40,0x9c5233cb,0xae5f33e4,0xb357a93b,0xb2feac26,0x2fc8b3ba,0x3245b258,0x30f830e0,
  0x30553179,0xb2ba31d6,0xb3df2e99,0xa9b6b34a,0xb39230fd,0xad2fb241,0x3200b301,0x314a2fbd,0x337f1b11,0xad993400,0xb3ff2deb,0xa084b36f,
  0xb005b129,0x32ebb21d,0x325c2cdb,0xb0db339f,0xa92233de,0xb3e529cf,0xab59b2b6,0x33c9b05a,0xb3dd30b2,0xa9e8b27a,0x33d4ab71,0xaa9433c8,
  0x32212c0e,0xb12433bd,0xaf64b0d6,0x3318b260,0x197fb345,0x3400aeaf,0xae4833fe,0xb35c20e8,0xb23d3332,0xb102aeff,0x33aeb14f,0x2c7b31fc,
  0xb3fe3065,0xa14db2b0,0x2ebb307f,0xb342329e,0x300f2fa6,0xb2e53307,0x30d1b3f5,0x326426c3,0x302ab400,0x32d517db,0xb3e72e02,0x28f0b36a,
  0xb3fd2f6f,0x2343b316,0x2d46311f,0xb38e3225,0xb3f53015,0x2691b2e1,0xaf9b33eb,0xb30a288d,0x2a193166,0xb3da31e7,0x33d7aec6,0xaa63333f,
  0x3313b337,0x2f7a2ee8,0xa5fbb1f4,0x33f7b158,0xb1a1a8d7,0x31afb3e8,0xb36832d8,0xae0eb025,0xb3c22f85,0x2bd3b310,0xb3ea322d,0xa8a6b116,
  0xa8be32a9,0xb3e9306f,0x2bba3074,0xb3c332a5,0x33fdb111,0xa27a3231,0x3389b30d,0x2d5e2f90,0xa216b1aa,0x33feb1a6,0xaed2ae25,0x333db363,
  0xb3652edd,0x2e1ab33a,0xb1aa227a,0x31a6b3fd,0xaf853387,0xb3102d6a,0xb22d33fe,0xb116a216,0x32a9abd3,0xb06f33c2,0x307428a6,0xb2a533ea,
  0x3111b3e9,0x3231a8be,0x330db3c3,0x2f902bba,0xb2e12e31,0x3015b360,0x288db1a1,0x33ebb1af,0xb1e733f5,0xb1662691,0xb33f2f9b,0x2ec6b30a,
  0x2ee82a19,0xb33733da,0xb15833d7,0xb1f42a63,0x33e8b313,0x28d72f7a,0x302525fb,0xb2d833f7,0xb2392d81,0x3107b383,0x3307b3fe,0x2fa6214d,
  0xb35e33ec,0xae3ca874,0x97dbb00f,0x3400b2e5,0xa5c930b7,0xb3f83276,0xb316302a,0x2f6fb2d5,0x32b0aef4,0xb0653335,0xb29e33fd,0xb07f2343,
  0xb1702ccf,0x31dfb3a1,0x3345b124,0xaeaf3221,0xb3fc336c,0xa3a7adf7,0x3332b400,0x2eff997f,0xb0b23304,0xb27a2fb2,0x2b71b102,0x33c8b23d,
  0x2c0e29e8,0xb3bd33dd,0xb0d62a94,0x3260b3d4,0xb0892c1a,0x3297b3bc,0x2aad2842,0xb3d333ee,0xb3b0327e,0x2c6fb0ad,0x3241b035,0xb0fd32ce,
  0xb35933fc,0xae542406,0x3400b392,0x1b112d2f,0xaf5931da,0xb31b3174,0x321db37f,0x3129ad99,0xaf152ac6,0x332cb3d2,0xb1463293,0xb204308e,
  0xb281312e,0x30a8b219,0xab402f4e,0xb3cb331e,0xb3ef3371,0x2829addf,0x2c269c52,0xb3ba3400,0xb37c33f2,0xada52759,0x3179afc8,0xb1d632fe,
  0xacf32953,0x339cb3e3,0xb3fa33cc,0x2500ab28,0xb0942f21,0x3290b32a,0xb3d033fb,0xaade246a,0xb249317d,0x30f3b1d2,0xb2fb337a,0xafd22db1,
  0xb37332f1,0x2dd4aff3,0xb18b3254,0xb1c530e5,0xa96c27bd,0x33e2b3f1,0xb0452fdd,0x32c4b2f7,0xac3e2af7,0x33b7b3cf,0xb0ea3099,0x3250b28c,
  0xadbc2cff,0x3378b39a,0xb1823137,0x31cdb211,0xaf2c2e76,0x3327b352,0xb20d31c9,0x313cb186,0x313c3186,0xb20db1c9,0x2d0b2dc8,0xb398b376,
  0x309e30ee,0xb289b24d,0x2b0f2c4b,0xb3ceb3b5,0x2fe8304a,0xb2f4b2c1,0x27ef2985,0xb3f0b3e1,0x2e822f37,0xb34fb324,0x1ead24ce,0xb3ffb3fa,
  0xb2bdb209,0xb050b141,0xb290b32a,0x30942f21,0xb3b3b34c,0xac57ae8d,0xb0f3b1d2,0x3249317d,0xb400b3ef,0x1d1ba810,0xadd4aff3,0x337332f1,
  0xb39cb3e3,0x2cf32953,0xa500ab28,0x33fa33cc,0xae99b0f8,0x334a3245,0x33ff33b2,0x201f2c63,0x2438a9b6,0x33fc33df,0x332c33d2,0xaf15aac6,
  0x303a2ce7,0x32cb339e,0x30a83219,0xb281b12e,0x32ee31c0,0x2ffe3190,0x28292ddf,0xb3efb371,0x33b0327e,0x2c6f30ad,0xb241b035,0xb0fdb2ce,
  0x335933fc,0xae54a406,0xb400b392,0x1b11ad2f,0x2f5931da,0xb31bb174,0xb21db37f,0x31292d99,0xaaad2842,0xb3d3b3ee,0xa9cfb005,0x33de32eb,
  0x285b305f,0xb3edb2b3,0x2c0ea9e8,0x33bd33dd,0xb170accf,0xb1dfb3a1,0x33453124,0x2eaf3221,0xb3fcb36c,0x23a7adf7,0x33323400,0xaeff997f,
  0xb0b2b304,0x327a2fb2,0x2b713102,0xb3c8b23d,0xb400b2e5,0x17dbb00f,0x2e023264,0xb36ab0d1,0xaf6fb2d5,0x3316302a,0xb11fa8f0,0xb225b3e7,
  0x307f2343,0x329e33fd,0xb3d6b38e,0x2a7cad46,0x33f53342,0xa6c32ebb,0xac87b1e3,0x33ac316b,0x28d7af7a,0x33e83313,0xb2d8b3f7,0x3025a5fb,
  0x33eb31af,0x288d31a1,0x2bebae0e,0x33c03368,0x2ec6330a,0xb33faf9b,0x33fe3235,0x21b1310c,0xb1f4aa63,0xb158b3d7,0x2d5232a2,0xb38bb07a,
  0x33a7333d,0xacab2ed2,0x33f63162,0x262d31eb,0xaa4b301a,0xb3d8b2de,0x2a32326b,0xb3d9b0c7,0xb3f6b26f,0x265fb0c1,0xb3a9b020,0xac9fb2db,
  0x0e48b15d,0x340031f0,0xae1ab33a,0x33652edd,0xaed22e25,0xb33db363,0xb1eb0e48,0xb162b400,0xb2deb3a7,0x301aacab,0xb0c7b3f6,0x326b262d,
  0x30c1aa4b,0x326f33d8,0x32db2a32,0x302033d9,0x31f033f6,0xb15d265f,0x2edd33a9,0xb33aac9f,0xb2acb385,0x306aad76,0x2a19b166,0x33da31e7,
  0x3229a2de,0x311b33fd,0x33133337,0xaf7a2ee8,0x2e3133c5,0xb360aba2,0xb1a128d7,0xb1afb3e8,0xb3f5b015,0xa691b2e1,0xaf9bb3eb,0x330a288d,
  0x3154acc3,0x31f833a3,0x2ef433f8,0xb335a5c9,0x2d8133dc,0xb383aa01,0xb3feb065,0x214db2b0,0xb3ecb107,0x2874b239,0x300fafa6,0x32e53307,
  0x30b7ae3c,0x3276335e,0x302a3400,0xb2d517db,0x312433bd,0xb2212c0e,0xb318b260,0x2f64b0d6,0xb400aeaf,0x997fb345,0x335c20e8,0x2e4833fe,
  0x3102aeff,0x323d3332,0xac7b31fc,0xb3aeb14f,0x2a9433c8,0xb3d4ab71,0xb084b3e6,0x329ba909,0xb2ce2aad,0xb035b3d3,0x33e529cf,0x292233de,
  0x2d2fb241,0x339230fd,0xb14a2fbd,0xb200b301,0x2d993400,0xb37f1b11,0x2084b36f,0x33ff2deb,0xb2ebb21d,0x3005b129,0x30db339f,0xb25c2cdb,
  0xae5fb3e4,0x3357a93b,0xb190303a,0xb1c0b2cb,0x32453258,0xb0f830e0,0x2c63b2ee,0x33b22ffe,0xb3dfae99,0x29b6b34a,0x2ac633ff,0xb3d2a01f,
  0x339ea438,0x2ce733fc,0xb12eb32c,0x3219af15,0x33b8a78b,0x2c3233f2,0x2810b3b3,0x33ef2c57,0xb2c72e6b,0xb040b354,0x29533400,0xb3e31d1b,
  0x3141b133,0x32093215,0xaf21b39c,0x332aacf3,0xae8d32bd,0xb34cb050,0x317d3290,0xb1d23094,0x27bd33fb,0xb3f1249c,0x2fdd3327,0xb2f72f2c,
  0xaaf7b3e2,0x33cfa96c,0xb099b2c4,0x328cb045,0x2cff33b7,0xb39a2c3e,0x31373250,0xb21130ea,0xae76b378,0x3352adbc,0xb1c9b1cd,0x3186b182,
  0xb3ff1ead,0x1de4b3ff,0xb352adbc,0x2e76b378,0x33f1249c,0xa7bd33fb,0x32f72f2c,0xafdd3327,0xb3cfa96c,0x2af7b3e2,0xb28cb045,0x3099b2c4,
  0x339a2c3e,0xacff33b7,0x321130ea,0xb1373250,0x2953b400,0x33e31d1b,0x33ccadd4,0x2b283373,0xaf21339c,0xb32aacf3,0xb3fb2500,0x246ab3fa,
  0x317db290,0x31d23094,0x337a2ade,0xadb133d0,0xb2f130f3,0xaff3b249,0xb254afd2,0x30e5b2fb,0x339e2438,0xace733fc,0xb12e332c,0xb219af15,
  0xb190b03a,0x31c0b2cb,0x3371b0a8,0x2ddf3281,0x2c6332ee,0xb3b22ffe,0xb3f22829,0x2759b3ef,0x2ac6b3ff,0x33d2a01f,0x32932da5,0xb08e337c,
  0xaf0a33f3,0xb32fa727,0x2406b3b0,0x33fcac6f,0x3347b194,0x2ea431bc,0xb1743359,0xb1daae54,0xb3bc2565,0x2c1ab3f9,0x33eeaf59,0x2842331b,
  0x30ad3089,0xb27e3297,0xb2ceaaad,0x3035b3d3,0xb29ba909,0x3084b3e6,0x305f3030,0xb2b332d1,0x259732e8,0xb3f8300a,0x2ccfb3ed,0x33a1a85b,
  0x31b8b381,0x31992d8d,0xb36c31df,0xadf7b170,0xb3f42d3a,0x26f5b390,0x330423a7,0xafb233fc,0x316bb3d6,0x31e32a7c,0xb3832a01,0x2d81b3dc,
  0xb3bf2c87,0x2c02b3ac,0x28743239,0xb3ec3107,0x2b8931b3,0xb3c6319d,0x3276b35e,0x30b72e3c,0x31f8b3a3,0x31542cc3,0xb33525c9,0x2ef4b3f8,
  0x310c2beb,0xb23533c0,0x33abb267,0x2c9330cc,0x307ab3fe,0x32a2a1b1,0xb06aad76,0x32acb385,0xb3a52d52,0x2cb7b38b,0xb11b33fd,0xb229a2de,
  0x94b63273,0xb40030bc,0x3360aba2,0xae3133c5,0xb2de33a7,0xb01aacab,0xb0c733f6,0xb26b262d,0x30c12a4b,0xb26f33d8,0x32dbaa32,0xb02033d9,
  0x31f0b3f6,0x315d265f,0x2eddb3a9,0x333aac9f,0xb1eb8e48,0x3162b400,0xb3872e1a,0x2d6ab365,0xae25ad5e,0x3363b389,0x8e48b15d,0x3400b1f0,
  0xb3a7333d,0xacabaed2,0xb3f63162,0x262db1eb,0x2a4b301a,0xb3d832de,0xaa32326b,0xb3d930c7,0x33f6b26f,0x265f30c1,0x33a9b020,0xac9f32db,
  0x33c0b368,0x2beb2e0e,0x30cc94b6,0xb2673400,0x21b1b10c,0x33feb235,0x3385b3ab,0x2d762c93,0xb38b307a,0x2d52b2a2,0xa2deb06a,0x33fdb2ac,
  0xb0bc33a5,0xb2732cb7,0xb3c5311b,0x2ba2b229,0x26c32ebb,0xb3f53342,0xb3ac316b,0x2c87b1e3,0x336ab0d1,0xae023264,0xb19d33bf,0xb1b32c02,
  0x3225b3e7,0x311fa8f0,0x2cc32b89,0xb3a333c6,0xaa7cad46,0x33d6b38e,0x33dcb1f8,0xaa013154,0xb3fe3318,0x20e8af64,0x3381b3f8,0x2d8d2597,
  0xb14f335c,0xb1fc2e48,0x2d3ab199,0x3390b1b8,0x29092c7b,0xb3e633ae,0xb03026f5,0x32d1b3f4,0x32e8b084,0xb00a329b,0xb3ed32b3,0x285bb05f,
  0x29cfb005,0x33deb2eb,0xb05a325c,0xb2b630db,0xafbd2922,0x3301b3e5,0x27272b59,0xb3f333c9,0xb36f3200,0x2debb14a,0x31bcaf0a,0xb194332f,
  0xb39f33ff,0xacdba084,0x33f9b347,0xa5652ea4,0x3394b2ba,0xad233055,0xa438a9b6,0x33fcb3df,0x33e4b3f9,0x293b2533,0xb03a2ce7,0x32cbb39e,
  0x3258b357,0x30e0ae5f,0xb2ee31c0,0x2ffeb190,0x2e99b0f8,0x334ab245,0xb3ff33b2,0x201fac63,0xaf4230a3,0xb3213285,0x3133b040,0xb21532c7,
  0xa99e2d17,0xb3e03396,0x32bdb209,0xb0503141,0x278b1f76,0xb3f233ff,0x33b3b34c,0xac572e8d,0x2e6bac32,0xb35433b8,0x3400b3ef,0x1d1b2810,
  0xb289324d,0x309eb0ee,0xb3ce33b5,0x2b0fac4b,0xb2f432c1,0x2fe8b04a,0xb3f033e1,0x27efa985,0xb34f3324,0x2e82af37,0xb3ff33fa,0x1eada4ce,
  0xb3983376,0x2d0badc8,0xb3fb33ff,0xa49c1de4,0x351c35f6,0xac93a617,0xb8a3b93c,0x308d2a16,0x32f43448,0xb160afa5,0xb6a4b7fe,0x353a3389,
  0x2fa53160,0xb448b2f4,0xb389b53a,0x37fe36a4,0x26172c93,0xb5f6b51c,0xaa16b08d,0x393c38a3,0x34c3358c,0xac47a5b2,0xb85fb8f3,0x304229b1,
  0x327e33fd,0xb106af26,0xb63cb785,0x34e7330f,0x2f263106,0xb3fdb27e,0xb30fb4e7,0x3785363c,0x25b22c47,0xb58cb4c3,0xa9b1b042,0x38f3385f,
  0x346a3523,0xabf6a54d,0xb81ab8a8,0x2fef294d,0x3209336b,0xb0acaea7,0xb5d4b70a,0x34933294,0x2ea730ac,0xb36bb209,0xb294b493,0x370a35d4,
  0x254d2bf6,0xb523b46a,0xa94dafef,0x38a8381a,0x341334bc,0xab5fa4e9,0xb7a6b85a,0x2f5928e8,0x319432da,0xb052ae28,0xb56ab68d,0x343e3219,
  0x2e283052,0xb2dab194,0xb219b43e,0x368d356a,0x24e92b5f,0xb4bcb413,0xa8e8af59,0x385a37a6,0x33783456,0xaac8a484,0xb715b80a,0x2ec32884,
  0x3120324a,0xaff2ada9,0xb4ffb60e,0x33d3319e,0x2da92ff2,0xb24ab120,0xb19eb3d3,0x360e34ff,0x24842ac8,0xb456b378,0xa884aec3,0x380a3715,
  0x32cd33e3,0xaa31a420,0xb682b76f,0x2e2d281f,0x30ac31bb,0xaf3fad2a,0xb493b58d,0x33283122,0x2d2a2f3f,0xb1bbb0ac,0xb122b328,0x358d3493,
  0x24202a31,0xb3e3b2cd,0xa81fae2d,0x376f3682,0x3223331c,0xa999a376,0xb5ebb6c6,0x2d972776,0x3039312d,0xae8dacac,0xb426b50b,0x327c30a6,
  0x2cac2e8d,0xb12db039,0xb0a6b27c,0x350b3426,0x23762999,0xb31cb223,0xa776ad97,0x36c635eb,0x317a3257,0xa902a2ad,0xb552b61a,0x2d0026ad,
  0x2f8c309f,0xaddcac2e,0xb371b487,0x31cf3029,0x2c2e2ddc,0xb09faf8c,0xb029b1cf,0x34873371,0x22ad2902,0xb257b17a,0xa6adad00,0x361a3552,
  0x30d23194,0xa86ba1e4,0xb4b7b56a,0x2c6a25e4,0x2ea73012,0xad2aab5f,0xb294b402,0x31222f59,0x2b5f2d2a,0xb012aea7,0xaf59b122,0x34023294,
  0x21e4286b,0xb194b0d2,0xa5e4ac6a,0x356a34b7,0x302c30d2,0xa7a9a11b,0xb41ab4b7,0x2ba7251b,0x2dc22f0c,0xac79aa63,0xb1b6b2f7,0x30742e5f,
  0x2a632c79,0xaf0cadc2,0xae5fb074,0x32f731b6,0x211b27a9,0xb0d2b02c,0xa51baba7,0x34b7341a,0x2f0c3012,0xa67ba052,0xb2f7b402,0x2a7a2452,
  0x2cde2df5,0xab91a967,0xb0d7b1e8,0x2f8b2d65,0x29672b91,0xadf5acde,0xad65af8b,0x31e830d7,0x2052267b,0xb012af0c,0xa452aa7a,0x340232f7,
  0x2dc22ea7,0xa54d9f12,0xb1b6b294,0x294d2311,0x2bf62cde,0xaa31a86b,0xafefb0d7,0x2e2d2c6a,0x286b2a31,0xacdeabf6,0xac6aae2d,0x30d72fef,
  0x1f12254d,0xaea7adc2,0xa311a94d,0x329431b6,0x2c792d2a,0xa4209d7f,0xb074b122,0x281f217f,0x2a312b91,0xa8d0a6e0,0xae2daf8b,0x2cce2ade,
  0x26e028d0,0xab91aa31,0xaadeacce,0x2f8b2e2d,0x1d7f2420,0xad2aac79,0xa17fa81f,0x31223074,0x2a632b5f,0xa1e49bdb,0xae5faf59,0x25e41fdb,
  0x286b2967,0xa6e0a4e9,0xac6aad65,0x2ade28e8,0x24e926e0,0xa967a86b,0xa8e8aade,0x2d652c6a,0x1bdb21e4,0xab5faa63,0x9fdba5e4,0x2f592e5f,
  0x27a9286b,0x9f1298b6,0xaba7ac6a,0x23111cb6,0x254d267b,0xa420a1e4,0xa94daa7a,0x281f25e4,0x21e42420,0xa67ba54d,0xa5e4a81f,0x2a7a294d,
  0x18b61f12,0xa86ba7a9,0x9cb6a311,0x2c6a2ba7,0x211b21e4,0x98b69248,0xa51ba5e4,0x1cb61648,0x1f122052,0x9d7f9bdb,0xa311a452,0x217f1fdb,
  0x1bdb1d7f,0xa0529f12,0x9fdba17f,0x24522311,0x124818b6,0xa1e4a11b,0x96489cb6,0x25e4251b,0xa11ba1e4,0x18b61248,0x251b25e4,0x9cb69648,
  0x9f12a052,0x1d7f1bdb,0x23112452,0xa17f9fdb,0x9bdb9d7f,0x20521f12,0x1fdb217f,0xa452a311,0x924898b6,0x21e4211b,0x16481cb6,0xa5e4a51b,
  0xa7a9a86b,0x1f1218b6,0x2ba72c6a,0xa3119cb6,0xa54da67b,0x242021e4,0x294d2a7a,0xa81fa5e4,0xa1e4a420,0x267b254d,0x25e4281f,0xaa7aa94d,
  0x98b69f12,0x286b27a9,0x1cb62311,0xac6aaba7,0xaa63ab5f,0x21e41bdb,0x2e5f2f59,0xa5e49fdb,0xa86ba967,0x26e024e9,0x2c6a2d65,0xaadea8e8,
  0xa4e9a6e0,0x2967286b,0x28e82ade,0xad65ac6a,0x9bdba1e4,0x2b5f2a63,0x1fdb25e4,0xaf59ae5f,0xac79ad2a,0x24201d7f,0x30743122,0xa81fa17f,
  0xaa31ab91,0x28d026e0,0x2e2d2f8b,0xacceaade,0xa6e0a8d0,0x2b912a31,0x2ade2cce,0xaf8bae2d,0x9d7fa420,0x2d2a2c79,0x217f281f,0xb122b074,
  0xadc2aea7,0x254d1f12,0x31b63294,0xa94da311,0xabf6acde,0x2a31286b,0x2fef30d7,0xae2dac6a,0xa86baa31,0x2cde2bf6,0x2c6a2e2d,0xb0d7afef,
  0x9f12a54d,0x2ea72dc2,0x2311294d,0xb294b1b6,0xaf0cb012,0x267b2052,0x32f73402,0xaa7aa452,0xacdeadf5,0x2b912967,0x30d731e8,0xaf8bad65,
  0xa967ab91,0x2df52cde,0x2d652f8b,0xb1e8b0d7,0xa052a67b,0x30122f0c,0x24522a7a,0xb402b2f7,0xb02cb0d2,0x27a9211b,0x341a34b7,0xaba7a51b,
  0xadc2af0c,0x2c792a63,0x31b632f7,0xb074ae5f,0xaa63ac79,0x2f0c2dc2,0x2e5f3074,0xb2f7b1b6,0xa11ba7a9,0x30d2302c,0x251b2ba7,0xb4b7b41a,
  0xb0d2b194,0x286b21e4,0x34b7356a,0xac6aa5e4,0xaea7b012,0x2d2a2b5f,0x32943402,0xb122af59,0xab5fad2a,0x30122ea7,0x2f593122,0xb402b294,
  0xa1e4a86b,0x319430d2,0x25e42c6a,0xb56ab4b7,0xb17ab257,0x290222ad,0x3552361a,0xad00a6ad,0xaf8cb09f,0x2ddc2c2e,0x33713487,0xb1cfb029,
  0xac2eaddc,0x309f2f8c,0x302931cf,0xb487b371,0xa2ada902,0x3257317a,0x26ad2d00,0xb61ab552,0xb223b31c,0x29992376,0x35eb36c6,0xad97a776,
  0xb039b12d,0x2e8d2cac,0x3426350b,0xb27cb0a6,0xacacae8d,0x312d3039,0x30a6327c,0xb50bb426,0xa376a999,0x331c3223,0x27762d97,0xb6c6b5eb,
  0xb2cdb3e3,0x2a312420,0x3682376f,0xae2da81f,0xb0acb1bb,0x2f3f2d2a,0x3493358d,0xb328b122,0xad2aaf3f,0x31bb30ac,0x31223328,0xb58db493,
  0xa420aa31,0x33e332cd,0x281f2e2d,0xb76fb682,0xb378b456,0x2ac82484,0x3715380a,0xaec3a884,0xb120b24a,0x2ff22da9,0x34ff360e,0xb3d3b19e,
  0xada9aff2,0x324a3120,0x319e33d3,0xb60eb4ff,0xa484aac8,0x34563378,0x28842ec3,0xb80ab715,0xb413b4bc,0x2b5f24e9,0x37a6385a,0xaf59a8e8,
  0xb194b2da,0x30522e28,0x356a368d,0xb43eb219,0xae28b052,0x32da3194,0x3219343e,0xb68db56a,0xa4e9ab5f,0x34bc3413,0x28e82f59,0xb85ab7a6,
  0xb46ab523,0x2bf6254d,0x381a38a8,0xafefa94d,0xb209b36b,0x30ac2ea7,0x35d4370a,0xb493b294,0xaea7b0ac,0x336b3209,0x32943493,0xb70ab5d4,
  0xa54dabf6,0x3523346a,0x294d2fef,0xb8a8b81a,0xb4c3b58c,0x2c4725b2,0x385f38f3,0xb042a9b1,0xb27eb3fd,0x31062f26,0x363c3785,0xb4e7b30f,
  0xaf26b106,0x33fd327e,0x330f34e7,0xb785b63c,0xa5b2ac47,0x358c34c3,0x29b13042,0xb8f3b85f,0xb51cb5f6,0x2c932617,0x38a3393c,0xb08daa16,
  0xb2f4b448,0x31602fa5,0x36a437fe,0xb53ab389,0xafa5b160,0x344832f4,0x3389353a,0xb7feb6a4,0xa617ac93,0x35f6351c,0x2a16308d,0xb93cb8a3,
};
__device__ __align__(128) const uint32_t c_img[2560] = {
  0x326d31ed,0x333b32dd,0x33c33388,0x33fe33ea,0x33c331ed,0x31ed33c3,0xa8b22d64,0xb33bb0c4,0x33ea31ed,0xad64301d,0xb2ddb388,0x315fa8b2,
  0x32dd31ed,0xb3feabc6,0x326dad64,0xad64326d,0x30c431ed,0xaed7b2dd,0x2bc63388,0xa248b3ea,0x2bc631ed,0x315fb3c3,0xb3ea2d64,0x2ed730c4,
  0xa8b231ed,0x3388b01d,0x301db388,0xb1ed28b2,0xb01d31ed,0x22482bc6,0x30c4ad64,0x3388b26d,0x33ea33fe,0x338833c3,0x32dd333b,0x31ed326d,
  0xb2ddb3fe,0xa248b01d,0x326d2ed7,0x338833ea,0x30c433fe,0xb33babc6,0xabc6b33b,0x33fe30c4,0xabc6b3fe,0x31ed32dd,0xb3eaaed7,0x333ba8b2,
  0xa8b233fe,0x2d64b3c3,0xb01d333b,0x315fb26d,0x301db3fe,0xb3fe301d,0x30c42ed7,0x2d64b3ea,0xb26d33fe,0x2ed72bc6,0x33c3b33b,0xa248b0c4,
  0x33c3b3fe,0x315fb2dd,0x28b2aed7,0xaed728b2,0xb0c4b15f,0xaed7b01d,0xabc6ad64,0xa248a8b2,0xabc6b15f,0x315f2bc6,0x33ea3388,0x2ed7326d,
  0x28b2b15f,0x338832dd,0xb01d2d64,0xb1edb3ea,0x301db15f,0x224833c3,0xb0c4b388,0x338830c4,0x326db15f,0xb33b301d,0x33c3ad64,0xb3fe28b2,
  0x33c3b15f,0xb1edabc6,0xa8b23388,0x333bb26d,0x33eab15f,0x2d64b2dd,0xb2dd2d64,0xb15f33ea,0x32ddb15f,0x33feb3c3,0x326db388,0x2d64b0c4,
  0x28b22248,0x2d642bc6,0x301d2ed7,0x315f30c4,0xb01da248,0xb3feb2dd,0xb0c4b33b,0x2d64a8b2,0x326d2248,0x2ed733c3,0xb3c3aed7,0xa248b26d,
  0xb3c3a248,0x315fb01d,0xa8b2333b,0xaed7b3ea,0x33ea2248,0xb388abc6,0x32dd2ed7,0xb1edb0c4,0xb2dda248,0x224832dd,0x326db33b,0xb38828b2,
  0x30c42248,0x333bb3c3,0xabc6aed7,0xb3fe326d,0xabc6a248,0xb1ed301d,0xb3ea333b,0xb33b33ea,0xb26d31ed,0xb33b32dd,0xb3c33388,0xb3fe33ea,
  0xb3c331ed,0xb1ed33c3,0x28b22d64,0x333bb0c4,0xb3ea31ed,0x2d64301d,0x32ddb388,0xb15fa8b2,0xb2dd31ed,0x33feabc6,0xb26dad64,0x2d64326d,
  0xb0c431ed,0x2ed7b2dd,0xabc63388,0x2248b3ea,0xabc631ed,0xb15fb3c3,0x33ea2d64,0xaed730c4,0x28b231ed,0xb388b01d,0xb01db388,0x31ed28b2,
  0x301d31ed,0xa2482bc6,0xb0c4ad64,0xb388b26d,0xb3ea33fe,0xb38833c3,0xb2dd333b,0xb1ed326d,0x32ddb3fe,0x2248b01d,0xb26d2ed7,0xb38833ea,
  0xb0c433fe,0x333babc6,0x2bc6b33b,0xb3fe30c4,0x2bc6b3fe,0xb1ed32dd,0x33eaaed7,0xb33ba8b2,0x28b233fe,0xad64b3c3,0x301d333b,0xb15fb26d,
  0xb01db3fe,0x33fe301d,0xb0c42ed7,0xad64b3ea,0x326d33fe,0xaed72bc6,0xb3c3b33b,0x2248b0c4,0xb3c3b3fe,0xb15fb2dd,0xa8b2aed7,0x2ed728b2,
  0x30c4b15f,0x2ed7b01d,0x2bc6ad64,0x2248a8b2,0x2bc6b15f,0xb15f2bc6,0xb3ea3388,0xaed7326d,0xa8b2b15f,0xb38832dd,0x301d2d64,0x31edb3ea,
  0xb01db15f,0xa24833c3,0x30c4b388,0xb38830c4,0xb26db15f,0x333b301d,0xb3c3ad64,0x33fe28b2,0xb3c3b15f,0x31edabc6,0x28b23388,0xb33bb26d,
  0xb3eab15f,0xad64b2dd,0x32dd2d64,0x315f33ea,0xb2ddb15f,0xb3feb3c3,0xb26db388,0xad64b0c4,0xa8b22248,0xad642bc6,0xb01d2ed7,0xb15f30c4,
  0x301da248,0x33feb2dd,0x30c4b33b,0xad64a8b2,0xb26d2248,0xaed733c3,0x33c3aed7,0x2248b26d,0x33c3a248,0xb15fb01d,0x28b2333b,0x2ed7b3ea,
  0xb3ea2248,0x3388abc6,0xb2dd2ed7,0x31edb0c4,0x32dda248,0xa24832dd,0xb26db33b,0x338828b2,0xb0c42248,0xb33bb3c3,0x2bc6aed7,0x33fe326d,
  0x2bc6a248,0x31ed301d,0x33ea333b,0x333b33ea,0x30c4315f,0x2ed7301d,0x2bc62d64,0x224828b2,0x2bc6315f,0xb15fabc6,0xb3eab388,0xaed7b26d,
  0xa8b2315f,0xb388b2dd,0x301dad64,0x31ed33ea,0xb01d315f,0xa248b3c3,0x30c43388,0xb388b0c4,0xb26d315f,0x333bb01d,0xb3c32d64,0x33fea8b2,
  0xb3c3315f,0x31ed2bc6,0x28b2b388,0xb33b326d,0xb3ea315f,0xad6432dd,0x32ddad64,0x315fb3ea,0xb2dd315f,0xb3fe33c3,0xb26d3388,0xad6430c4,
  0xa8b2a248,0xad64abc6,0xb01daed7,0xb15fb0c4,0x301d2248,0x33fe32dd,0x30c4333b,0xad6428b2,0xb26da248,0xaed7b3c3,0x33c32ed7,0x2248326d,
  0x33c32248,0xb15f301d,0x28b2b33b,0x2ed733ea,0xb3eaa248,0x33882bc6,0xb2ddaed7,0x31ed30c4,0x32dd2248,0xa248b2dd,0xb26d333b,0x3388a8b2,
  0xb0c4a248,0xb33b33c3,0x2bc62ed7,0x33feb26d,0x2bc62248,0x31edb01d,0x33eab33b,0x333bb3ea,0x326d31ed,0x333b32dd,0x33c33388,0x33fe33ea,
  0x33c331ed,0x31ed33c3,0xa8b22d64,0xb33bb0c4,0x33ea31ed,0xad64301d,0xb2ddb388,0x315fa8b2,0x32dd31ed,0xb3feabc6,0x326dad64,0xad64326d,
  0x30c431ed,0xaed7b2dd,0x2bc63388,0xa248b3ea,0x2bc631ed,0x315fb3c3,0xb3ea2d64,0x2ed730c4,0xa8b231ed,0x3388b01d,0x301db388,0xb1ed28b2,
  0xb01d31ed,0x22482bc6,0x30c4ad64,0x3388b26d,0x33ea33fe,0x338833c3,0x32dd333b,0x31ed326d,0xb2ddb3fe,0xa248b01d,0x326d2ed7,0x338833ea,
  0x30c433fe,0xb33babc6,0xabc6b33b,0x33fe30c4,0xabc6b3fe,0x31ed32dd,0xb3eaaed7,0x333ba8b2,0xa8b233fe,0x2d64b3c3,0xb01d333b,0x315fb26d,
  0x301db3fe,0xb3fe301d,0x30c42ed7,0x2d64b3ea,0xb26d33fe,0x2ed72bc6,0x33c3b33b,0xa248b0c4,0x33c3b3fe,0x315fb2dd,0x28b2aed7,0xaed728b2,
  0xb0c4315f,0xaed7301d,0xabc62d64,0xa24828b2,0xabc6315f,0x315fabc6,0x33eab388,0x2ed7b26d,0x28b2315f,0x3388b2dd,0xb01dad64,0xb1ed33ea,
  0x301d315f,0x2248b3c3,0xb0c43388,0x3388b0c4,0x326d315f,0xb33bb01d,0x33c32d64,0xb3fea8b2,0x33c3315f,0xb1ed2bc6,0xa8b2b388,0x333b326d,
  0x33ea315f,0x2d6432dd,0xb2ddad64,0xb15fb3ea,0x32dd315f,0x33fe33c3,0x326d3388,0x2d6430c4,0x28b2a248,0x2d64abc6,0x301daed7,0x315fb0c4,
  0xb01d2248,0xb3fe32dd,0xb0c4333b,0x2d6428b2,0x326da248,0x2ed7b3c3,0xb3c32ed7,0xa248326d,0xb3c32248,0x315f301d,0xa8b2b33b,0xaed733ea,
  0x33eaa248,0xb3882bc6,0x32ddaed7,0xb1ed30c4,0xb2dd2248,0x2248b2dd,0x326d333b,0xb388a8b2,0x30c4a248,0x333b33c3,0xabc62ed7,0xb3feb26d,
  0xabc62248,0xb1edb01d,0xb3eab33b,0xb33bb3ea,0xb26d31ed,0xb33b32dd,0xb3c33388,0xb3fe33ea,0xb3c331ed,0xb1ed33c3,0x28b22d64,0x333bb0c4,
  0xb3ea31ed,0x2d64301d,0x32ddb388,0xb15fa8b2,0xb2dd31ed,0x33feabc6,0xb26dad64,0x2d64326d,0xb0c431ed,0x2ed7b2dd,0xabc63388,0x2248b3ea,
  0xabc631ed,0xb15fb3c3,0x33ea2d64,0xaed730c4,0x28b231ed,0xb388b01d,0xb01db388,0x31ed28b2,0x301d31ed,0xa2482bc6,0xb0c4ad64,0xb388b26d,
  0xb3ea33fe,0xb38833c3,0xb2dd333b,0xb1ed326d,0x32ddb3fe,0x2248b01d,0xb26d2ed7,0xb38833ea,0xb0c433fe,0x333babc6,0x2bc6b33b,0xb3fe30c4,
  0x2bc6b3fe,0xb1ed32dd,0x33eaaed7,0xb33ba8b2,0x28b233fe,0xad64b3c3,0x301d333b,0xb15fb26d,0xb01db3fe,0x33fe301d,0xb0c42ed7,0xad64b3ea,
  0x326d33fe,0xaed72bc6,0xb3c3b33b,0x2248b0c4,0xb3c3b3fe,0xb15fb2dd,0xa8b2aed7,0x2ed728b2,0x29ed29ed,0x29ed29ed,0x29ed29ed,0x29ed29ed,
  0x2bc32a6d,0x2add2bea,0x23c628c4,0xa81da0b2,0x2bc32add,0xa3c6281d,0xabc3aadd,0x23c6a81d,0x29ed2b3b,0xabfea564,0x295fa6d7,0x1a482b88,
  0x25642b88,0xa564ab88,0x25642b88,0xa564ab88,0xa0b22bc3,0x2a6daadd,0xabea23c6,0x28c4281d,0xa8c42bea,0x2a6da0b2,0x28c4abea,0xaa6d20b2,
  0xab3b2bfe,0xa564295f,0x26d79a48,0x2b88a9ed,0x29ed29ed,0x29ed29ed,0x29ed29ed,0x29ed29ed,0xabc3aa6d,0xaaddabea,0xa3c6a8c4,0x281d20b2,
  0x2bc32add,0xa3c6281d,0xabc3aadd,0x23c6a81d,0xa9edab3b,0x2bfe2564,0xa95f26d7,0x9a48ab88,0x25642b88,0xa564ab88,0x25642b88,0xa564ab88,
  0x20b2abc3,0xaa6d2add,0x2beaa3c6,0xa8c4a81d,0xa8c42bea,0x2a6da0b2,0x28c4abea,0xaa6d20b2,0x2b3babfe,0x2564a95f,0xa6d71a48,0xab8829ed,
  0x295f295f,0x295f295f,0x295f295f,0x295f295f,0x23c628c4,0xa81da0b2,0xabc3aa6d,0xaaddabea,0xa3c6281d,0xabc3aadd,0x23c6a81d,0x2bc32add,
  0xa95f26d7,0x9a48ab88,0x29ed2b3b,0xabfea564,0xab882564,0x2b88a564,0xab882564,0x2b88a564,0xabea23c6,0x28c4281d,0x20b2abc3,0xaa6d2add,
  0xaa6d20b2,0xa8c42bea,0x2a6da0b2,0x28c4abea,0xa6d71a48,0xab8829ed,0xab3b2bfe,0xa564295f,0x295f295f,0x295f295f,0x295f295f,0x295f295f,
  0xa3c6a8c4,0x281d20b2,0x2bc32a6d,0x2add2bea,0xa3c6281d,0xabc3aadd,0x23c6a81d,0x2bc32add,0x295fa6d7,0x1a482b88,0xa9edab3b,0x2bfe2564,
  0xab882564,0x2b88a564,0xab882564,0x2b88a564,0x2beaa3c6,0xa8c4a81d,0xa0b22bc3,0x2a6daadd,0xaa6d20b2,0xa8c42bea,0x2a6da0b2,0x28c4abea,
  0x26d79a48,0x2b88a9ed,0x2b3babfe,0x2564a95f,0xabfe2bfe,0xabfe2bfe,0xabfe2bfe,0xabfe2bfe,0xaadd2bea,0xa3c628c4,0x281da0b2,0x2bc3aa6d,
  0xa81d2bc3,0x2adda3c6,0x281dabc3,0xaadd23c6,0x9a482b88,0x29edab3b,0xabfe2564,0x295f26d7,0x26d72b3b,0xa6d7ab3b,0x26d72b3b,0xa6d7ab3b,
  0x2a6d2add,0xabeaa3c6,0x28c4a81d,0x20b22bc3,0x2bea2a6d,0xa0b228c4,0xabeaaa6d,0x20b2a8c4,0x2b8829ed,0x2b3b2bfe,0x2564295f,0xa6d79a48,
  0xabfe2bfe,0xabfe2bfe,0xabfe2bfe,0xabfe2bfe,0x2addabea,0x23c6a8c4,0xa81d20b2,0xabc32a6d,0xa81d2bc3,0x2adda3c6,0x281dabc3,0xaadd23c6,
  0x1a48ab88,0xa9ed2b3b,0x2bfea564,0xa95fa6d7,0x26d72b3b,0xa6d7ab3b,0x26d72b3b,0xa6d7ab3b,0xaa6daadd,0x2bea23c6,0xa8c4281d,0xa0b2abc3,
  0x2bea2a6d,0xa0b228c4,0xabeaaa6d,0x20b2a8c4,0xab88a9ed,0xab3babfe,0xa564a95f,0x26d71a48,0x1a489a48,0x1a489a48,0x1a489a48,0x1a489a48,
  0x281da0b2,0x2bc3aa6d,0x2addabea,0x23c6a8c4,0x2adda3c6,0x281dabc3,0xaadd23c6,0xa81d2bc3,0x2bfea564,0xa95fa6d7,0x9a482b88,0x29edab3b,
  0x2b3ba6d7,0xab3b26d7,0x2b3ba6d7,0xab3b26d7,0x28c4a81d,0x20b22bc3,0xaa6daadd,0x2bea23c6,0x20b2a8c4,0x2bea2a6d,0xa0b228c4,0xabeaaa6d,
  0xa564a95f,0x26d71a48,0x2b8829ed,0x2b3b2bfe,0x1a489a48,0x1a489a48,0x1a489a48,0x1a489a48,0xa81d20b2,0xabc32a6d,0xaadd2bea,0xa3c628c4,
  0x2adda3c6,0x281dabc3,0xaadd23c6,0xa81d2bc3,0xabfe2564,0x295f26d7,0x1a48ab88,0xa9ed2b3b,0x2b3ba6d7,0xab3b26d7,0x2b3ba6d7,0xab3b26d7,
  0xa8c4281d,0xa0b2abc3,0x2a6d2add,0xabeaa3c6,0x20b2a8c4,0x2bea2a6d,0xa0b228c4,0xabeaaa6d,0x2564295f,0xa6d79a48,0xab88a9ed,0xab3babfe,
  0xa95fa95f,0xa95fa95f,0xa95fa95f,0xa95fa95f,0xa3c6a8c4,0x281d20b2,0x2bc32a6d,0x2add2bea,0x23c6a81d,0x2bc32add,0xa3c6281d,0xabc3aadd,
  0x295fa6d7,0x1a482b88,0xa9edab3b,0x2bfe2564,0x2b88a564,0xab882564,0x2b88a564,0xab882564,0x2beaa3c6,0xa8c4a81d,0xa0b22bc3,0x2a6daadd,
  0x2a6da0b2,0x28c4abea,0xaa6d20b2,0xa8c42bea,0x26d79a48,0x2b88a9ed,0x2b3babfe,0x2564a95f,0xa95fa95f,0xa95fa95f,0xa95fa95f,0xa95fa95f,
  0x23c628c4,0xa81da0b2,0xabc3aa6d,0xaaddabea,0x23c6a81d,0x2bc32add,0xa3c6281d,0xabc3aadd,0xa95f26d7,0x9a48ab88,0x29ed2b3b,0xabfea564,
  0x2b88a564,0xab882564,0x2b88a564,0xab882564,0xabea23c6,0x28c4281d,0x20b2abc3,0xaa6d2add,0x2a6da0b2,0x28c4abea,0xaa6d20b2,0xa8c42bea,
  0xa6d71a48,0xab8829ed,0xab3b2bfe,0xa564295f,0x29ed29ed,0x29ed29ed,0x29ed29ed,0x29ed29ed,0x2bc32a6d,0x2add2bea,0x23c628c4,0xa81da0b2,
  0x2bc32add,0xa3c6281d,0xabc3aadd,0x23c6a81d,0x29ed2b3b,0xabfea564,0x295fa6d7,0x1a482b88,0x25642b88,0xa564ab88,0x25642b88,0xa564ab88,
  0xa0b22bc3,0x2a6daadd,0xabea23c6,0x28c4281d,0xa8c42bea,0x2a6da0b2,0x28c4abea,0xaa6d20b2,0xab3b2bfe,0xa564295f,0x26d79a48,0x2b88a9ed,
  0x29ed29ed,0x29ed29ed,0x29ed29ed,0x29ed29ed,0xabc3aa6d,0xaaddabea,0xa3c6a8c4,0x281d20b2,0x2bc32add,0xa3c6281d,0xabc3aadd,0x23c6a81d,
  0xa9edab3b,0x2bfe2564,0xa95f26d7,0x9a48ab88,0x25642b88,0xa564ab88,0x25642b88,0xa564ab88,0x20b2abc3,0xaa6d2add,0x2beaa3c6,0xa8c4a81d,
  0xa8c42bea,0x2a6da0b2,0x28c4abea,0xaa6d20b2,0x2b3babfe,0x2564a95f,0xa6d71a48,0xab8829ed,0x9a481a48,0x9a481a48,0x9a481a48,0x9a481a48,
  0xa81d20b2,0xabc32a6d,0xaadd2bea,0xa3c628c4,0xaadd23c6,0xa81d2bc3,0x2adda3c6,0x281dabc3,0xabfe2564,0x295f26d7,0x1a48ab88,0xa9ed2b3b,
  0xab3b26d7,0x2b3ba6d7,0xab3b26d7,0x2b3ba6d7,0xa8c4281d,0xa0b2abc3,0x2a6d2add,0xabeaa3c6,0xa0b228c4,0xabeaaa6d,0x20b2a8c4,0x2bea2a6d,
  0x2564295f,0xa6d79a48,0xab88a9ed,0xab3babfe,0x9a481a48,0x9a481a48,0x9a481a48,0x9a481a48,0x281da0b2,0x2bc3aa6d,0x2addabea,0x23c6a8c4,
  0xaadd23c6,0xa81d2bc3,0x2adda3c6,0x281dabc3,0x2bfea564,0xa95fa6d7,0x9a482b88,0x29edab3b,0xab3b26d7,0x2b3ba6d7,0xab3b26d7,0x2b3ba6d7,
  0x28c4a81d,0x20b22bc3,0xaa6daadd,0x2bea23c6,0xa0b228c4,0xabeaaa6d,0x20b2a8c4,0x2bea2a6d,0xa564a95f,0x26d71a48,0x2b8829ed,0x2b3b2bfe,
  0xabfe2bfe,0xabfe2bfe,0xabfe2bfe,0xabfe2bfe,0xaadd2bea,0xa3c628c4,0x281da0b2,0x2bc3aa6d,0xa81d2bc3,0x2adda3c6,0x281dabc3,0xaadd23c6,
  0x9a482b88,0x29edab3b,0xabfe2564,0x295f26d7,0x26d72b3b,0xa6d7ab3b,0x26d72b3b,0xa6d7ab3b,0x2a6d2add,0xabeaa3c6,0x28c4a81d,0x20b22bc3,
  0x2bea2a6d,0xa0b228c4,0xabeaaa6d,0x20b2a8c4,0x2b8829ed,0x2b3b2bfe,0x2564295f,0xa6d79a48,0xabfe2bfe,0xabfe2bfe,0xabfe2bfe,0xabfe2bfe,
  0x2addabea,0x23c6a8c4,0xa81d20b2,0xabc32a6d,0xa81d2bc3,0x2adda3c6,0x281dabc3,0xaadd23c6,0x1a48ab88,0xa9ed2b3b,0x2bfea564,0xa95fa6d7,
  0x26d72b3b,0xa6d7ab3b,0x26d72b3b,0xa6d7ab3b,0xaa6daadd,0x2bea23c6,0xa8c4281d,0xa0b2abc3,0x2bea2a6d,0xa0b228c4,0xabeaaa6d,0x20b2a8c4,
  0xab88a9ed,0xab3babfe,0xa564a95f,0x26d71a48,0x3bfb3bff,0x3be53bf2,0x3bbf3bd4,0x3b873ba5,0x3bd03bfb,0x3b013b7c,0x399d3a60,0x378538bc,
  0x35173b52,0xbbc9b7c8,0xb074ba9b,0x3bfe391b,0x319e3b27,0xbbf3b979,0x363cb80a,0x3a2d3bc5,0xba093986,0x3a7eb8f8,0xbae5385f,0x3b3db77a,
  0xbabd393c,0x3bb0b699,0xbc00305b,0x3ba730d7,0xbb2a35c8,0xb8353bb2,0x3a64b1e8,0x3962bbf7,0xba90350b,0xba413bff,0x3602340e,0x3bf6bad8,
  0xac6aa5e4,0xb122af59,0xb402b294,0xb56ab4b7,0xb2deac9c,0xb7bdb5a5,0xb9b3b8d6,0xbb10ba73,0xbb96b676,0xb359bafe,0x3bec3884,0x2a163a29,
  0xbbe0b72c,0x2f27b9d6,0x3b5e3ae8,0xb91633a2,0xb941b9c9,0x38ad3a45,0xb80fbab3,0x36d23b13,0xb850ba0d,0x346f3b4a,0x1fdbbbed,0xb4ab3be8,
  0x3721bb76,0xbace3463,0xb8d13bdd,0x39ebadfb,0x3894bb98,0xb8fd281f,0xbb6a3bbd,0x2e2d3825,0x3b3f3b65,0x3ae83b16,0x3a813ab6,0x3a0d3a49,
  0x3263356a,0xad972b43,0xb5dfb359,0xb8eeb7f3,0xa9b139aa,0xbbedba25,0x3340b889,0x3b983afb,0xbaa2aa16,0xb4cfbb8e,0x3c0038ad,0xb44b38e5,
  0xbb853625,0x3bbdb4c3,0xbbe432ad,0x3bfbaf8b,0xbaacb6d2,0x39243954,0xb65fbace,0x2fbd3bb8,0xb9661648,0xba603bf8,0x383a31cf,0x3b27bbb3,
  0x3219b9eb,0xbb1836f4,0xb9903be5,0x37dd3010,0xb6c6b61a,0xb80ab76f,0xb8a8b85a,0xb93cb8f3,0xbbd7bb87,0xbbf8bbfd,0xbb71bbc9,0xba4dbaf1,
  0xbbfeb9a6,0x305bb91f,0x3bcb3a97,0xb50b37d2,0xb87abbfe,0x3ba13546,0x24523a7e,0xbbb5ba54,0xb576bb63,0x340e3ba3,0xb13bbbd3,0x2c9c3bf2,
  0x386abb3d,0xba2139f8,0x3b57b835,0xbbf13432,0x39e7bc00,0xb8d6adc9,0xbacb3bde,0x372c3457,0x3bdab962,0x3764bb35,0xb9c03122,0xbaf73bef,
  0x398b39cd,0x38fd3946,0x386538b2,0x37853815,0xba85b9c9,0xbb92bb1e,0xbbfebbdd,0xbbc2bbf5,0xb66b3682,0xbb01bb94,0x387fb371,0x3a2d3beb,
  0xbac7bb76,0x3a00ad33,0x36bb3bd4,0xbbeab79b,0xbc0026ad,0x3bf32c38,0xbbd6b109,0x3ba733eb,0x3153bbff,0xb70a3b9e,0x396bba9b,0xbade390c,
  0xb5d4b5bc,0xbbb03b2c,0x32013830,0x3bf6ba67,0x3bccbb52,0x2c06b92e,0xbb83385f,0xb8c73bab,0xb9c5b982,0xba41ba04,0xbab0ba7a,0xbb10bae1,
  0xb8a3b986,0xb52fb74e,0xa94db1e8,0x33d32e91,0xbb54bb4f,0x37bdb523,0x3a9e3bc8,0xb916308d,0x3840b5c8,0x394a3bf9,0xbb42b294,0xb0a6bb0a,
  0x251bbbff,0xaf273bfc,0x327cbbe6,0xb4ab3bc0,0x3be325e4,0xbb2fb4e7,0x39e33884,0xb81aba35,0x3b73bb78,0xb46fb715,0xbbdc3ad1,0x2e2d38cc,
  0x33283676,0x3bfcba19,0x3581bab3,0xba6b3493,0x363136dd,0x34cf3581,0x32c6341a,0x2fbd3153,0xbae1bb65,0xb970ba39,0xb715b889,0xb16cb4f3,
  0xb9a12a7a,0xb924bbfe,0x3a933042,0x37dd3bcc,0x308db9aa,0x3b453b07,0xb94632ad,0xb845bbfa,0xbb68b55e,0x3b1836bb,0xbabab805,0x3a4d38a3,
  0x3bc0b625,0xbbfe2ec3,0x3b9431cf,0xba89b742,0x9cb6b95d,0xbbf8396b,0xb1b63a5c,0x3bb5b840,0x38cc9648,0x3b81bbac,0xac38b85a,0xbbce3933,
  0xbb60bb3a,0xbba1bb83,0xbbd2bbbc,0xbbf1bbe3,0x3815361a,0x39df3907,0x3b2c3a97,0x3be23b9c,0xb9afbbfd,0x3a21294d,0x388e3bee,0xbaf7b328,
  0x3beb39a6,0xb6af37a6,0xba04bbd3,0x3ac42d00,0x360ebb89,0xb7643b42,0x3855baeb,0xb8ee3a85,0x33eb3b63,0x28e8bbf5,0xb5233bde,0x389ebb21,
  0x3c00b9f0,0x2d97b9e3,0xbbdf38db,0xb44b3ac7,0xba673c00,0x358d3487,0x3bfcbab6,0x330fba15,0x3b7a3bf1,0x394a3a93,0x33893764,0xb3d39cb6,
  0x3afb3be2,0x35eb3946,0xb4c328e8,0xbaa9b8cc,0x27763af7,0xbb2fbaba,0x3a76ad97,0x30a63b60,0xaf8b3ac4,0xb994bb94,0x3bf8358d,0xb8743815,
  0xbb4c38ee,0x3bfcb1b6,0xbad5b4cf,0x381a39af,0xbbb3389e,0x3b592c38,0xb76fb970,0xb24b3beb,0xb9d2344b,0xbb923bd2,0xb0f03924,0x3a6bb60e,
  0xb8f3330f,0xbc003b2c,0xb91f3b45,0x323233eb,0xb5b1afbd,0xba00b88e,0xbbc6bb18,0xbbc2bc00,0xb7d2b16c,0xbb6fba04,0xbba3bbfe,0xb86fba67,
  0xbbffb7dd,0x370ab855,0x38b73bf8,0xbbeab631,0xbbf2b845,0x39bcb523,0x2dc93b81,0xbaa5bae1,0xb68dba4d,0xac063bdf,0x382abba1,0xbade39a1,
  0xb457ba89,0xb6543bfc,0x3b16b9df,0xbbd8308d,0x397dbbb5,0xb52fb2c6,0xbbe73a21,0xb8c73b68,0x3a49bbce,0x2311b715,0xba2536af,0xbbd93bc0,
  0xb958b785,0xbb81ba9e,0xbbefbbf3,0xba89bb73,0xbbf7bbc2,0xb9b8bb42,0xaf59b70a,0x384a3328,0xbb8bba2d,0x39dfb27c,0x34263bb0,0xbbceb98b,
  0xb4b7bbea,0x3b6c39e3,0xbafe2c06,0x3185ba85,0xaadebba7,0xb6af3bdc,0x3a58ba41,0xbbe2366b,0x3a29bade,0xbc003581,0x3a45352f,0xb2f7bac7,
  0x3b37bbf6,0x28e8b865,0xbaee37bd,0xbac43c00,0x3b13b8c7,0x3b5cbbfe,0x3463b94a,0xb8993153,0xb9f4bb10,0xb58db87f,0x3029af27,0x389e35d4,
  0x2dfbb3d3,0x399936bb,0x3bf23b2f,0x3ac13bcc,0x3552b916,0x39703bd6,0xbbbab46f,0x330fb9c5,0x3ba530a6,0xb5f7396b,0xb7c8bbfc,0x3be138a3,
  0x3bfdb4ab,0xbb45b201,0x38e038fd,0xb16cbb54,0x391b381a,0xa17fbb83,0xb8f83b92,0x3bcfb840,0x36e82e2d,0x3bfebab0,0x37febb01,0xb845251b,
  0xb77a3a6b,0x3648294d,0x3bb2ba00,0x3a8cbbe3,0xb742b93c,0x2311b340,0x37a6340e,0x3aa93966,0x3b963a4d,0x3b7f3c00,0x380f3a21,0xb0be3219,
  0x3933b50b,0x35eb3be4,0xbbf5b8d6,0x3874b6c6,0x39413bb5,0xbbffb65f,0x38d1b764,0x33ba3bd7,0x3b9c2c9c,0xb994b83a,0x34873ae8,0x324bbbfe,
  0xb7213bf1,0x3b47b990,0xbbbf2d97,0x38c1387a,0x2d00372c,0x3b59b8a8,0x3a39bbed,0xb232b576,0xbbfb3af7,0xb9743b71,0x307434cf,0x3adbb86a,
  0x3b213a0d,0x3c003bcb,0x3b073bbd,0x386f39e7,0x351738ee,0xb599a452,0xbae5b924,0xbbe9bbda,0x3a153b98,0xbb6fb13b,0x2ec3ba60,0x3aa53b3f,
  0xba09344b,0xa884bb57,0x3a643b18,0xbbc3b263,0xb4f33bfb,0x39bcbacb,0xbbac380a,0x3bd8a9b1,0xbb2aafbd,0x36a439c0,0x3402bbf8,0xba6f3aa2,
  0xbbfa3b27,0xb6543a81,0x3907b05b,0x3bd9bb85,0x2c6ab7dd,0xb9da35df,0xbbec3ba1,0xb8203aac,0x3bf53b87,0x3b6c3bec,0x392e3a7e,0x32f73721,
  0xb9e7b785,0xbbfcbb5e,0xba81bbb0,0xb43eb894,0x379b3bfe,0xbc00b80f,0x374eb835,0x38993bfb,0xbb3fba2d,0x3b329fdb,0xb3403a41,0xb8eabbd0,
  0xb90c3b3d,0x3b5cb8d1,0xbbf93122,0x3ac13517,0x29b1bba7,0xb94f3b6a,0x3be4b7bd,0xbaf4b19e,0xbbab3962,0xb9993bbf,0x34e73359,0x3be1ba09,
  0x3b85bbf6,0x353ab99d,0xb83a2f27,0xbbf03abd,0x2e91356a,0xb5f7b074,0xba19b8ad,0xbbcfbb2a,0xb966bb10,0xaba7b63c,0x38a8346f,0x3bb73a90,
  0xbb0aaa16,0xa17fbae5,0x3b1e3ace,0xba8c2c6a,0x36c6b916,0x36ff3c00,0xbbcbb8fd,0x3a50b2de,0xba35b6d2,0x36483a64,0x2d33bbe5,0xb84a3b96,
  0x3bfeb4ab,0xb9fcb602,0x313b3b01,0x37e8bbe0,0x3493b9eb,0xb9b83402,0xbb9e3bc9,0xb1853941,0x35762e2d,0x3b90b9b3,0x3acbbbf3,0x2fefb850,
  0x3a543bcf,0x2884374e,0xb9f8b648,0xbbe9bbab,0x398b3bb7,0xb4db3340,0xbbdcb9fc,0xb911bb85,0xb4323a8c,0xb6a4bbf9,0x3b3539b8,0xbbc3ae91,
  0xb66b3a50,0xad65bbe4,0x38653b90,0xbb0db966,0xbbef384a,0x39da34e7,0x2b43bb6c,0xba6f3b0a,0xbc0037e8,0x3759383a,0x387fbbfc,0xbbf636c6,
  0xb7f33185,0xbb7f3a19,0xbb8e3c00,0xb8203a35,0xb5d42fef,0xba1d38a8,0xbbd63b32,0xbba93bfe,0xb8e5b2f7,0xbbffbb1e,0xb954bb5c,0x30beb493,
  0xb9c5b43e,0xbb9fbbcb,0xb201b94f,0x3a313576,0xbbb8b899,0x3b47ad33,0xb6f43999,0xb3babbf5,0xbb54b8ea,0x3bf9313b,0xbab0353a,0x3790b9e7,
  0xb010bac1,0xb9743b9e,0x3bfdb5f7,0xb8c1b79b,0x251bbaf4,0xbb1b3acb,0x3a9e2ba7,0x2e5fbb3f,0x3af1bbe1,0x3599b92e,0xb546a17f,0xbadb390c,
  0x3b73bbf0,0x3929ba81,0x327cb6ff,0xb49f29b1,0xb825baa9,0x353aaec3,0x3b7c3994,0x3af43bfa,0x360eb0be,0x3bf43a64,0x388e3b47,0xb7372c6a,
  0x38bcb874,0x2ba73bac,0xb979bb59,0x3bf03742,0x3c0033ba,0xbb043402,0x3855b974,0xacce3b96,0x3bc5b24b,0xb6ffb907,0xb6993c00,0x3bb7b933,
  0x363138c1,0x3902bbec,0xbbdf3599,0x34ff3941,0x30d73232,0x39fcb7a6,0x3bffbb6f,0x3a50bb9c,0xb9a13adb,0xb47b380f,0x32c62884,0x3937b721,
  0x3ad8386f,0x3b903bf5,0x35a539bc,0xb7e8ad00,0x3b683be9,0x2ef538d1,0xba93b6a4,0xbb24bbfb,0x3a733aa5,0xbbfcb487,0x39d6b654,0xafef3b21,
  0x1cb63bc3,0xb7b2bbbf,0x3aba39da,0xbbfab517,0xb3a23bd8,0x3b32ba39,0xbb4a2311,0x343e3a15,0xbb603a6f,0x3a3d3074,0x31b6bb7f,0xbb9a3a09,
  0xbbe83bd9,0xb94f3b07,0xa81f35eb,0x38eab4f3,0xb9af3820,0xbbae3ae5,0xbbd23bff,0xba113b2a,0x319e389e,0xb929b426,0xbc00bb45,0xb911bb37,
  0xbbffbac1,0xb805bafe,0x382a217f,0x3bfd3b13,0xbabd330f,0x34dbba58,0x36023bfe,0xbb0db9f4,0xb68dbbe1,0x3a5c3a45,0xbbe7b648,0x3b89adfb,
  0xba90b16c,0x2d653aee,0x39b3bb81,0xbbf63552,0x397dbbcf,0xbbbc3463,0x338939b8,0x39f0bba5,0x32deb845,0xb7593029,0xbb5e39df,0xbba93bfd,
  0x3b7aba8c,0x3beebbf2,0x3a76bb6c,0x36ddb91b,0xbbe0ba89,0xba1dbbba,0x1fdbb6af,0x3a3136e8,0xa776b84a,0x3aeb37c8,0x3ad53c00,0xaa7a377a,
  0xb850bbce,0x3b9f38e0,0xbb6a28e8,0x3790b958,0x3b4cb185,0xb8db38f8,0x30f0bb5c,0x355e3bf7,0x3894bbe2,0xbbf937fe,0x399d358d,0x2e5fbb8b,
  0x39d232f7,0x341abbb2,0xbbc63999,0x395d34b7,0x3bd0bac4,0x3b1bbbef,0x363cb970,0xb49faade,0xb5b13899,0x30422f59,0x38b7b5f7,0x3b3aba29,
  0x3219b3d3,0x3b0438b7,0x3b713bfc,0x34ff397d,0x36e83aa9,0xb8b2adc9,0xbbefbb59,0xb5bcba49,0x3bd730a6,0xb902382a,0xa452bb92,0x39373b7a,
  0xb9583874,0x3371bb16,0x34263c00,0xb982bafb,0x387a381a,0x347bbbe7,0xbb573a00,0x3b242776,0xbb8b324b,0x31093a25,0x3a58bb6f,0xbb4f2f8b,
  0xb86a3a6b,0x2ef53389,0x39c0b70a,0x3bfabb4c,0xaadeb232,0xb83034c3,0xbaee39bc,0xbbff3bb3,0x3bda3bc2,0x37b23a76,0xb5df2c06,0xbb9ab9d2,
  0xbb37b86f,0xba7abbf8,0x3029b654,0x3b7838f3,0x32633bea,0xba3dbad5,0x3c00352f,0xba1135b1,0xb9f4baa5,0x3bc8376f,0xbbba2311,0x39cdb7d2,
  0xbaa23ade,0x3baeb0f0,0xb65fb94a,0xb7373bff,0x3552bbd8,0xbbe6391f,0x38e035eb,0x3682bbf2,0xbaac38c7,0xbbf43bc6,0xb9903b2f,0xacce368d,
  0x3bfdbbd9,0x3ad1bba3,0x37feb994,0x26adb457,0x38a33b9a,0xb8dba452,0xbb83bbae,0x2a7ab86a,0x37423b78,0xbab6b426,0xb907bbe6,0x39aa2ade,
  0xb8403a11,0x341abb57,0x294d3bf4,0xb55ebbda,0xb93339cd,0x3889ba58,0xb7a63ad1,0x3625bb37,0xbbe33737,0x304239c0,0x3b42bb04,0xb95db263,
  0xbb9c3682,0xb2ad3aee,0x3bf5b8b2,0x1648b9f4,0xb3282cce,0xb80535df,0xb9e33902,0xbb3a3aa2,0xad0026ad,0xb1cf3029,0xb4873371,0xb61a3552,
  0xba85b4ff,0xba5cbc00,0x3581b47b,0x3bfd3aac,0xbb21b5bc,0xb85abbba,0x3a393109,0x39a63bfd,0xbac7b937,0x3bbc365f,0xbbfeaef5,0x3b89b219,
  0xba15b982,0x3a9738e0,0xbb07b830,0x3b6336e8,0x3153bb24,0xbbee3990,0x36bb37b2,0x39f0bbd7,0x34f3bb4f,0xbbd337fe,0xaec33a7a,0x3c00b958,
  0x3bccbbfa,0x3aebbb71,0x396bba3d,0x36ddb87a,0x3bfabbff,0x3bdebbef,0x3bacbbc8,0x3b65bb8b,0x3bc03911,0x38303b6a,0xb946ad65,0xbb4fbbd0,
  0x3a353bfd,0xb85f30f0,0xbb1ebbbc,0x35c8b5b1,0x38cc3b0d,0xba7ab99d,0x3b943759,0xbbffb19e,0xb4933b89,0x31e8bbc6,0xad333bee,0xa5e4bbff,
  0xb8153bf6,0x3bc8b63c,0xac38ba1d,0xbb783abd,0xbbf539f0,0x329438b7,0x3b9ebaeb,0xb676b68d,0xbbeb3ba9,0xbbe63c00,0xbb2c3b9f,0xb9cd3a90,
  0xb79b36dd,0xb884382a,0xb92e38db,0xb9c9397d,0x33eb3a31,0xbad1b602,0xba04bbf9,0x3682b2de,0xb90c2a7a,0xbab3bbe7,0x374eb41a,0x3b763b7a,
  0xba673790,0x38b2b9b3,0xb5233b1b,0x26adbbe0,0xbbabb55e,0x3bdd3389,0xbbf9b042,0x3bff2776,0xbae12e5f,0xb3713b5e,0x3bfcb929,0xb5bcb850,
  0xae91b95d,0xbbd43a76,0x34e73805,0x3b52bb4c,0x308db49f,0xb1091fdb,0xb71534db,0xb9823894,0x3b0abb3a,0x3a9bbad5,0x3a19ba5c,0x3986b9d2,
  0x2f8bb7e8,0x3bde3979,0x376f3b32,0xb9aab0d7,0x3bb83b24,0xb1223855,0xbbfdba3d,0xaa16b9a1,0x3bb3afef,0xbab63699,0x391fb94f,0xb6253ad8,
  0x30103bfa,0xb359bbdf,0x35463bae,0xb6d2bb68,0x38f3343e,0x3889bbff,0xbba3353a,0x96483a73,0xbaf13b9a,0x38ad32c6,0x39f8bbf4,0xb9eb9cb6,
  0xb7d238ea,0xb2ad35a5,0x2dc92ba7,0x361ab3a2,0xba543a11,0xbace3a93,0xbb353b04,0xbb873b60,0x3bf23af4,0x31cf39d6,0xbb16b6ff,0xb9a6bbe8,
  0xb4323737,0xbbe5baba,0x2b43b902,0x3bfe39af,0x34573bf0,0xb85abb4a,0x3a2539fc,0xbb63b825,0xbbef2cce,0x3bc9b1b6,0xbb8e347b,0x3b3db60e,
  0xba493bb7,0x3a97a81f,0x34c3bb90,0xbc0038bc,0xb7f3b4ff,0xba7e3bd2,0x39542ef5,0x3962bc00,0xbafb3a50,0xbbd33b7c,0xbbf83bfc,0xbb653bc5,
  0x38e5b937,0x3835b88e,0x36f4b7b2,0x356ab631,0xbb13bbe9,0x31e8b6f4,0x3bf239da,0x36763af1,0x3be83911,0x340e3ab0,0xbb7cb759,0xb72cbb73,
  0x2dfbbbc3,0x32943bfd,0xb7c8bb7f,0x39c93a54,0x38253b0d,0xb8d6ba9e,0x39793a1d,0xba0db98b,0x3ba5ba6f,0xb884b546,0xb8f83bff,0x3b76b432,
  0xb8bc3bf6,0x3ae8b27c,0x3699bb9f,0xbb98366b,0x391bb820,0x3ab3b9f8,0x3bb2bb47,0x3bffbbef,0xbbc53ba9,0xbbed3bdc,0xbbff3bf9,0xbbfb3c00,
  0x377ab0be,0x3bdd3b35,0x2f593974,0xbb52b7f3,0x30d73a31,0xbbbdb865,0xb5a5bb1b,0x3b2735d4,0x3bf733ba,0xbbd42b43,0x3afeb599,0xb98638e5,
  0xbad83790,0x3a60b87f,0xb9d63929,0x393cb9c5,0x34b738c1,0x3a9bbb8e,0xba45a884,0xb5c83bb8,0xba732e5f,0xb80a3bd6,0x3b4ab4db,0x350bbb54,
  0xba293adb,0xb85f3954,0xb46336a4,0x25e43010,0x33a2b49f,0x305bb201,0x281fad65,0xac9c251b,0x3f803f80,0x3f803f80,0x3f803f80,0x3f803f80,
  0x3f803f80,0x3f803f80,0x3f803f80,0x3f803f80,0x3f803f80,0x3f803f80,0x3f803f80,0x3f803f80,0x3f803f80,0x3f803f80,0x3f803f80,0x3f803f80,
  0x3f803f80,0x3f803f80,0x3f803f80,0x3f803f80,0x3f803f80,0x3f803f80,0x3f803f80,0x3f803f80,0x3f803f80,0x3f803f80,0x3f803f80,0x3f803f80,
  0x3f803f80,0x3f803f80,0x3f803f80,0x3f803f80,0x3f803f80,0x3f803f80,0x3f803f80,0x3f803f80,0x3f803f80,0x3f803f80,0x3f803f80,0x3f803f80,
  0x3f803f80,0x3f803f80,0x3f803f80,0x3f803f80,0x3f803f80,0x3f803f80,0x3f803f80,0x3f803f80,0x3f803f80,0x3f803f80,0x3f803f80,0x3f803f80,
  0x3f803f80,0x3f803f80,0x3f803f80,0x3f803f80,0x3f803f80,0x3f803f80,0x3f803f80,0x3f803f80,0x3f803f80,0x3f803f80,0x3f803f80,0x3f803f80,
  0x3f803f80,0x3f803f80,0x3f803f80,0x3f803f80,0x3f803f80,0x3f803f80,0x3f803f80,0x3f803f80,0x3f803f80,0x3f803f80,0x3f803f80,0x3f803f80,
  0x3f803f80,0x3f803f80,0x3f803f80,0x3f803f80,0x3f803f80,0x3f803f80,0x3f803f80,0x3f803f80,0x3f803f80,0x3f803f80,0x3f803f80,0x3f803f80,
  0x3f803f80,0x3f803f80,0x3f803f80,0x3f803f80,0x3f803f80,0x3f803f80,0x3f803f80,0x3f803f80,0x3f803f80,0x3f803f80,0x3f803f80,0x3f803f80,
  0x3f803f80,0x3f803f80,0x3f803f80,0x3f803f80,0x3f803f80,0x3f803f80,0x3f803f80,0x3f803f80,0x3f803f80,0x3f803f80,0x3f803f80,0x3f803f80,
  0x3f803f80,0x3f803f80,0x3f803f80,0x3f803f80,0x3f803f80,0x3f803f80,0x3f803f80,0x3f803f80,0x3f803f80,0x3f803f80,0x3f803f80,0x3f803f80,
  0x3f803f80,0x3f803f80,0x3f803f80,0x3f803f80,0x3f803f80,0x3f803f80,0x3f803f80,0x3f803f80,0x3f803f80,0x3f803f80,0x3f803f80,0x3f803f80,
  0x3f803f80,0x3f803f80,0x3f803f80,0x3f803f80,0x3f803f80,0x3f803f80,0x3f803f80,0x3f803f80,0x3f803f80,0x3f803f80,0x3f803f80,0x3f803f80,
  0x3f803f80,0x3f803f80,0x3f803f80,0x3f803f80,0x3f803f80,0x3f803f80,0x3f803f80,0x3f803f80,0x3f803f80,0x3f803f80,0x3f803f80,0x3f803f80,
  0x3f803f80,0x3f803f80,0x3f803f80,0x3f803f80,0x3f803f80,0x3f803f80,0x3f803f80,0x3f803f80,0x3f803f80,0x3f803f80,0x3f803f80,0x3f803f80,
  0x3f803f80,0x3f803f80,0x3f803f80,0x3f803f80,0x3f803f80,0x3f803f80,0x3f803f80,0x3f803f80,0x3f803f80,0x3f803f80,0x3f803f80,0x3f803f80,
  0x3f803f80,0x3f803f80,0x3f803f80,0x3f803f80,0x3f803f80,0x3f803f80,0x3f803f80,0x3f803f80,0x3f803f80,0x3f803f80,0x3f803f80,0x3f803f80,
  0x3f803f80,0x3f803f80,0x3f803f80,0x3f803f80,0x3f803f80,0x3f803f80,0x3f803f80,0x3f803f80,0x3f803f80,0x3f803f80,0x3f803f80,0x3f803f80,
  0x3f803f80,0x3f803f80,0x3f803f80,0x3f803f80,0x3f803f80,0x3f803f80,0x3f803f80,0x3f803f80,0x3f803f80,0x3f803f80,0x3f803f80,0x3f803f80,
  0x3f803f80,0x3f803f80,0x3f803f80,0x3f803f80,0x3f803f80,0x3f803f80,0x3f803f80,0x3f803f80,0x3f803f80,0x3f803f80,0x3f803f80,0x3f803f80,
  0x3f803f80,0x3f803f80,0x3f803f80,0x3f803f80,0x3f803f80,0x3f803f80,0x3f803f80,0x3f803f80,0x3f803f80,0x3f803f80,0x3f803f80,0x3f803f80,
  0x3f803f80,0x3f803f80,0x3f803f80,0x3f803f80,0x3f803f80,0x3f803f80,0x3f803f80,0x3f803f80,0x3f803f80,0x3f803f80,0x3f803f80,0x3f803f80,
  0x3f803f80,0x3f803f80,0x3f803f80,0x3f803f80,0x3f803f80,0x3f803f80,0x3f803f80,0x3f803f80,0x3f803f80,0x3f803f80,0x3f803f80,0x3f803f80,
  0x3f803f80,0x3f803f80,0x3f803f80,0x3f803f80,0x3f803f80,0x3f803f80,0x3f803f80,0x3f803f80,0x3f803f80,0x3f803f80,0x3f803f80,0x3f803f80,
  0x3f803f80,0x3f803f80,0x3f803f80,0x3f803f80,0x3f803f80,0x3f803f80,0x3f803f80,0x3f803f80,0x3f803f80,0x3f803f80,0x3f803f80,0x3f803f80,
  0x3f803f80,0x3f803f80,0x3f803f80,0x3f803f80,0x3f803f80,0x3f803f80,0x3f803f80,0x3f803f80,0x3f803f80,0x3f803f80,0x3f803f80,0x3f803f80,
  0x3f803f80,0x3f803f80,0x3f803f80,0x3f803f80,0x3f803f80,0x3f803f80,0x3f803f80,0x3f803f80,0x3f803f80,0x3f803f80,0x3f803f80,0x3f803f80,
  0x3f803f80,0x3f803f80,0x3f803f80,0x3f803f80,0x3f803f80,0x3f803f80,0x3f803f80,0x3f803f80,0x3f803f80,0x3f803f80,0x3f803f80,0x3f803f80,
  0x3f803f80,0x3f803f80,0x3f803f80,0x3f803f80,0x3f803f80,0x3f803f80,0x3f803f80,0x3f803f80,0x3f803f80,0x3f803f80,0x3f803f80,0x3f803f80,
  0x3f803f80,0x3f803f80,0x3f803f80,0x3f803f80,0x3f803f80,0x3f803f80,0x3f803f80,0x3f803f80,0x3f803f80,0x3f803f80,0x3f803f80,0x3f803f80,
  0x3f803f80,0x3f803f80,0x3f803f80,0x3f803f80,0x3f803f80,0x3f803f80,0x3f803f80,0x3f803f80,0x3f803f80,0x3f803f80,0x3f803f80,0x3f803f80,
  0x3f803f80,0x3f803f80,0x3f803f80,0x3f803f80,0x3f803f80,0x3f803f80,0x3f803f80,0x3f803f80,0x3f803f80,0x3f803f80,0x3f803f80,0x3f803f80,
  0x3f803f80,0x3f803f80,0x3f803f80,0x3f803f80,0x3f803f80,0x3f803f80,0x3f803f80,0x3f803f80,0x3f803f80,0x3f803f80,0x3f803f80,0x3f803f80,
  0x3f803f80,0x3f803f80,0x3f803f80,0x3f803f80,0x3f803f80,0x3f803f80,0x3f803f80,0x3f803f80,0x3f803f80,0x3f803f80,0x3f803f80,0x3f803f80,
  0x3f803f80,0x3f803f80,0x3f803f80,0x3f803f80,0x3f803f80,0x3f803f80,0x3f803f80,0x3f803f80,0x3f803f80,0x3f803f80,0x3f803f80,0x3f803f80,
  0x3f803f80,0x3f803f80,0x3f803f80,0x3f803f80,0x3f803f80,0x3f803f80,0x3f803f80,0x3f803f80,0x3f803f80,0x3f803f80,0x3f803f80,0x3f803f80,
  0x3f803f80,0x3f803f80,0x3f803f80,0x3f803f80,0x3f803f80,0x3f803f80,0x3f803f80,0x3f803f80,0x3f803f80,0x3f803f80,0x3f803f80,0x3f803f80,
  0x3f803f80,0x3f803f80,0x3f803f80,0x3f803f80,0x3f803f80,0x3f803f80,0x3f803f80,0x3f803f80,0x3f803f80,0x3f803f80,0x3f803f80,0x3f803f80,
  0x3f803f80,0x3f803f80,0x3f803f80,0x3f803f80,0x3f803f80,0x3f803f80,0x3f803f80,0x3f803f80,0x3f803f80,0x3f803f80,0x3f803f80,0x3f803f80,
  0x3f803f80,0x3f803f80,0x3f803f80,0x3f803f80,0x3f803f80,0x3f803f80,0x3f803f80,0x3f803f80,0x3f803f80,0x3f803f80,0x3f803f80,0x3f803f80,
  0x3f803f80,0x3f803f80,0x3f803f80,0x3f803f80,0x3f803f80,0x3f803f80,0x3f803f80,0x3f803f80,0x3f803f80,0x3f803f80,0x3f803f80,0x3f803f80,
  0x3f803f80,0x3f803f80,0x3f803f80,0x3f803f80,0x3f803f80,0x3f803f80,0x3f803f80,0x3f803f80,0x3f803f80,0x3f803f80,0x3f803f80,0x3f803f80,
  0x3f803f80,0x3f803f80,0x3f803f80,0x3f803f80,0x3f803f80,0x3f803f80,0x3f803f80,0x3f803f80,0x3f803f80,0x3f803f80,0x3f803f80,0x3f803f80,
  0x3f803f80,0x3f803f80,0x3f803f80,0x3f803f80,
};

__device__ __align__(128) float    g_part[16][8][2176];
__device__ __align__(128) float    g_kv[16][2176];
constexpr int OBLK = 16 * 1024 + 32;
__device__ __align__(128) uint4    g_o[16 * OBLK];
#define GSTAMP(role, i) do {} while (0)
#define STAMP(role, i) do {} while (0)
#define PDUMP(role) do {} while (0)
#define PROF_SMEM 0

constexpr int STAGE_BYTES = 57344;
constexpr int OFF_H = 4 * 16384, OFF_VP = 9 * 16384, OFF_SPARE = 10 * 16384;
constexpr int OFF_XT = 172032, XT_STRIDE = 4112;
constexpr int OFF_BAR = 204928, OFF_EPOCH = OFF_BAR + 640, OFF_EX = OFF_BAR + 656, OFF_D = OFF_BAR + 672, OFF_SCALE = OFF_BAR + 704;
constexpr int OFF_F2F = 205824, OFF_F2I = 207872, OFF_F4 = 209920, OFF_ONES = 214016, OFF_KVB = 214016;
constexpr int OFF_STG = 219136, STG_STRIDE = 4352, SMEM_TOTAL = 232192 + PROF_SMEM;
enum { B_FULL1 = 0, B_EMPTY1 = 3, B_Q = 6, B_ODONE1 = 7, B_O1RDY = 8, B_H = 9, B_XRAW = 10, B_XT = 11, B_KV = 12, B_Y = 13,  B_AFREE = 15,
       B_STG = 18, B_ODONE = 24, B_XFREE = 25, B_FULL2 = 33, B_CONS2 = 49, B_SFREE = 14, B_KV1 = 61, B_OLOC = 60, B_PKRDY = 62, B_PKFREE = 64, B_H2 = 65, B_G1DONE = 66, B_COUNT = 67, B_FIRST = 67 };
constexpr uint64_t SLOT_A = 0x6859468594685948ull, SLOT_B = 0x7103271032710326ull;
constexpr int NPRE = 6, BEARLY = 3;
__host__ __device__ constexpr int bar_count(int i) {
  return i < B_EMPTY1 ? 1 : i < B_Q ? 4 : i == B_XT ? 4 : i == B_H ? 4 : (i == B_SFREE || i == B_G1DONE) ? 2 : i >= B_PKFREE ? 4 : i >= B_PKRDY ? 8 : i == B_Y ? 9
       : (i >= B_AFREE && i < B_STG) ? 16 : (i == B_ODONE || i == B_ODONE1) ? 8 : (i >= B_XFREE && i < B_FULL2) ? 4
       : i == B_KV1 ? 1 : i == B_OLOC ? 2 : i >= B_CONS2 ? 4 : (i >= B_FULL2 && i < B_FULL2 + NPRE) ? 2 : 1;
}
__host__ __device__ constexpr uint64_t bar_counts(int r) {
  uint64_t v = 0;
  for (int w = 0; w < 11; w++) v |= (uint64_t)(bar_count(1 + 11 * r + w) - 1) << (4 * w);
  return v;
}
constexpr uint32_t SW128 = 64 | (1u << 30);
constexpr int SPIN_LIMIT = 1 << 22;
#define OLOC 1
#define G2E 1
#define G2P 1
#define RC 200
#define PFD 3
#define PD1 700
#define PD2 450
#define QPF 6
#define BPACE 250
#define OCH 3
#define O1D 0
#define HOLD2 12
#define D1 100
#define TRICK 3
#define HSTART 1500
#define PACE 800

__device__ __forceinline__ uint32_t smem_u32(const void* p) { return (uint32_t)__cvta_generic_to_shared(p); }
__device__ __forceinline__ void wg_fence() { asm volatile("wgmma.fence.sync.aligned;" ::: "memory"); }
__device__ __forceinline__ void wg_commit() { asm volatile("wgmma.commit_group.sync.aligned;" ::: "memory"); }
template <int N> __device__ __forceinline__ void wg_wait() { asm volatile("wgmma.wait_group.sync.aligned %0;" ::"n"(N) : "memory"); }
template <int N> __device__ __forceinline__ void keep(float (&d)[N]) {
#pragma unroll
  for (int i = 0; i < N; i++) asm volatile("" : "+f"(d[i])::"memory");
}
__device__ __forceinline__ void mbar_init(uint32_t bar, int cnt) { asm volatile("mbarrier.init.shared::cta.b64 [%0], %1;" ::"r"(bar), "r"(cnt)); }
__device__ __forceinline__ void mbar_expect(uint32_t bar, int bytes) { asm volatile("mbarrier.arrive.expect_tx.shared::cta.b64 _, [%0], %1;" ::"r"(bar), "r"(bytes) : "memory"); }
__device__ __forceinline__ void mbar_arrive(uint32_t bar) { asm volatile("mbarrier.arrive.shared::cta.b64 _, [%0];" ::"r"(bar) : "memory"); }
__device__ __forceinline__ void mbar_arrive_cl(uint32_t bar, uint32_t cta) {
  asm volatile("{\n.reg .b32 r;\nmapa.shared::cluster.u32 r, %0, %1;\nmbarrier.arrive.shared::cluster.b64 _, [r];\n}\n" ::"r"(bar), "r"(cta) : "memory");
}
__device__ __forceinline__ void mbar_wait(uint32_t bar, uint32_t parity) {
  asm volatile("{\n.reg .pred p;\n.reg .u32 n;\nmov.u32 n, 0;\n"
               "W_%=:\nmbarrier.try_wait.parity.shared::cta.b64 p, [%0], %1;\n@p bra D_%=;\n"
               "add.u32 n, n, 1;\nsetp.lt.u32 p, n, %2;\n@p bra W_%=;\ntrap;\nD_%=:\n}\n" ::"r"(bar), "r"(parity), "n"(SPIN_LIMIT) : "memory");
}
__device__ __forceinline__ void fence_async() { asm volatile("fence.proxy.async.shared::cta;" ::: "memory"); }
__device__ __forceinline__ void bar_sync(int id) { asm volatile("bar.sync %0, 128;" ::"r"(id) : "memory"); }
__device__ __forceinline__ void tma2d(uint32_t dst, const CUtensorMap* m, int c0, int c1, uint32_t bar) {
  asm volatile("cp.async.bulk.tensor.2d.shared::cluster.global.mbarrier::complete_tx::bytes [%0], [%1, {%3, %4}], [%2];"
               ::"r"(dst), "l"(m), "r"(bar), "r"(c0), "r"(c1) : "memory");
}
__device__ __forceinline__ void tma2d_mc(uint32_t dst, const CUtensorMap* m, int c0, int c1, uint32_t bar) {
  asm volatile("cp.async.bulk.tensor.2d.shared::cluster.global.mbarrier::complete_tx::bytes.multicast::cluster [%0], [%1, {%3, %4}], [%2], %5;"
               ::"r"(dst), "l"(m), "r"(bar), "r"(c0), "r"(c1), "h"((uint16_t)3) : "memory");
}
__device__ __forceinline__ void tma3d(uint32_t dst, const CUtensorMap* m, int c0, int c1, int c2, uint32_t bar) {
  asm volatile("cp.async.bulk.tensor.3d.shared::cluster.global.mbarrier::complete_tx::bytes [%0], [%1, {%3, %4, %5}], [%2];"
               ::"r"(dst), "l"(m), "r"(bar), "r"(c0), "r"(c1), "r"(c2) : "memory");
}
__device__ __forceinline__ void tma4d(uint32_t dst, const CUtensorMap* m, int c0, int c1, int c2, int c3, uint32_t bar) {
  asm volatile("cp.async.bulk.tensor.4d.shared::cluster.global.mbarrier::complete_tx::bytes [%0], [%1, {%3, %4, %5, %6}], [%2];"
               ::"r"(dst), "l"(m), "r"(bar), "r"(c0), "r"(c1), "r"(c2), "r"(c3) : "memory");
}
__device__ __forceinline__ void bulk_ld(uint32_t dst, const void* src, int bytes, uint32_t bar) {
  asm volatile("cp.async.bulk.shared::cluster.global.mbarrier::complete_tx::bytes [%0], [%1], %2, [%3];" ::"r"(dst), "l"(src), "r"(bytes), "r"(bar) : "memory");
}
__device__ __forceinline__ void bulk_ld_mc(uint32_t dst, const void* src, int bytes, uint32_t bar) {
  asm volatile("cp.async.bulk.shared::cluster.global.mbarrier::complete_tx::bytes.multicast::cluster [%0], [%1], %2, [%3], %4;"
               ::"r"(dst), "l"(src), "r"(bytes), "r"(bar), "h"((uint16_t)3) : "memory");
}
__device__ __forceinline__ void tma2d_st(const CUtensorMap* m, uint32_t src, int c0, int c1) {
  asm volatile("cp.async.bulk.tensor.2d.global.shared::cta.bulk_group [%0, {%2, %3}], [%1];" ::"l"(m), "r"(src), "r"(c0), "r"(c1) : "memory");
}
__device__ __forceinline__ void ldsm4(uint32_t (&r)[4], uint32_t a) {
  asm volatile("ldmatrix.sync.aligned.m8n8.x4.shared.b16 {%0,%1,%2,%3}, [%4];" : "=r"(r[0]), "=r"(r[1]), "=r"(r[2]), "=r"(r[3]) : "r"(a) : "memory");
}
__device__ __forceinline__ void ldsm4t(uint32_t (&r)[4], uint32_t a) {
  asm volatile("ldmatrix.sync.aligned.m8n8.x4.trans.shared.b16 {%0,%1,%2,%3}, [%4];" : "=r"(r[0]), "=r"(r[1]), "=r"(r[2]), "=r"(r[3]) : "r"(a) : "memory");
}
__device__ __forceinline__ void stsm4(uint32_t a, uint32_t r0, uint32_t r1, uint32_t r2, uint32_t r3) {
  asm volatile("stmatrix.sync.aligned.m8n8.x4.shared.b16 [%0], {%1,%2,%3,%4};" ::"r"(a), "r"(r0), "r"(r1), "r"(r2), "r"(r3) : "memory");
}
__device__ __forceinline__ uint32_t pk2(float lo, float hi) { uint32_t r; asm("cvt.rn.bf16x2.f32 %0, %1, %2;" : "=r"(r) : "f"(hi), "f"(lo)); return r; }
__device__ __forceinline__ uint32_t hmul(uint32_t a, uint32_t b) { uint32_t r; asm("mul.rn.bf16x2 %0, %1, %2;" : "=r"(r) : "r"(a), "r"(b)); return r; }
__device__ __forceinline__ uint32_t hadd(uint32_t a, uint32_t b) { uint32_t r; asm("add.rn.bf16x2 %0, %1, %2;" : "=r"(r) : "r"(a), "r"(b)); return r; }
__device__ __forceinline__ uint32_t hmaxabs(uint32_t a, uint32_t b) { uint32_t r; asm("max.xorsign.abs.bf16x2 %0, %1, %2;" : "=r"(r) : "r"(a), "r"(b)); return r; }
__device__ __forceinline__ float ex2(float x) { float r; asm("ex2.approx.ftz.f32 %0, %1;" : "=f"(r) : "f"(x)); return r; }
__device__ __forceinline__ float rcp_fast(float x) { float r; asm("rcp.approx.ftz.f32 %0, %1;" : "=f"(r) : "f"(x)); return r; }
__device__ __forceinline__ uint32_t phi2(float lo, float hi) {
  const float c = 1.4426950408889634f;
  uint32_t r;
  asm("max.bf16x2 %0, %1, %2;" : "=r"(r) : "r"(pk2(lo, hi)), "r"(hadd(pk2(ex2(-fabsf(fmaf(lo, c, -c))), ex2(-fabsf(fmaf(hi, c, -c)))), 0x35863586u)));
  return r;
}
__device__ __forceinline__ bool opaque_true() { uint32_t v; asm volatile("mov.u32 %0, %%nctaid.y;" : "=r"(v)); return v != 0; }
__device__ __forceinline__ int norm_exp(uint32_t (&v)[32], float f0) {
  uint32_t m[4] = {hmaxabs(__float_as_uint(f0) >> 16, v[0]), v[1], v[2], v[3]};
#pragma unroll
  for (int i = 4; i < 32; i++) m[i & 3] = hmaxabs(m[i & 3], v[i]);
  m[0] = hmaxabs(hmaxabs(m[0], m[1]), hmaxabs(m[2], m[3]));
  const int e = min(max((int)(__reduce_max_sync(~0u, max(m[0] & 0x7FFFu, (m[0] >> 16) & 0x7FFFu)) >> 7), 1), 253);
  if (e > 141) {
#pragma unroll
    for (int i = 0; i < 32; i++) v[i] = hmul(v[i], 0x07000700u);
  }
  return e;
}
__device__ __forceinline__ void norm_cvt(uint32_t (&v)[32], float f0, int e) {
  const uint32_t sc = (e > 141 ? 255 - e : 142 - e) * 0x00800080u;
#pragma unroll
  for (int i = 0; i < 32; i++) {
    const uint32_t a = hmul(v[i], sc);
    v[i] = (a & 0x0FFF0FFFu) * 7 + a;
  }
  v[0] = __byte_perm(v[0], __half_as_ushort(__float2half_rn(f0 * __uint_as_float((254 - e) << 23))), 0x3254);
}
__device__ __forceinline__ void poll_ge(const unsigned* p, unsigned target) {
#pragma unroll 1
  for (int n = 0; n < SPIN_LIMIT; n++) {
    unsigned v;
    asm volatile("ld.relaxed.gpu.global.u32 %0, [%1];" : "=r"(v) : "l"(p) : "memory");
    if (__all_sync(~0u, (int)(v - target) >= 0)) { asm volatile("fence.acquire.gpu;" ::: "memory"); return; }
  }
  __trap();
}

__device__ __forceinline__ bool elect_one() {
  uint32_t p;
  asm volatile("{\n.reg .pred p;\nelect.sync _|p, 0xffffffff;\nselp.u32 %0, 1, 0, p;\n}\n" : "=r"(p));
  return p;
}
__device__ __forceinline__ uint4 ld_na4(const void* p) {
  uint4 v;
  asm volatile("ld.global.L1::no_allocate.v4.u32 {%0,%1,%2,%3}, [%4];" : "=r"(v.x), "=r"(v.y), "=r"(v.z), "=r"(v.w) : "l"(p) : "memory");
  return v;
}
__device__ __forceinline__ void st_cg4(void* p, uint4 v) {
  asm volatile("st.global.cg.v4.u32 [%0], {%1,%2,%3,%4};" ::"l"(p), "r"(v.x), "r"(v.y), "r"(v.z), "r"(v.w) : "memory");
}
__device__ __forceinline__ uint32_t mapa(uint32_t a, uint32_t cta) { uint32_t r; asm("mapa.shared::cluster.u32 %0, %1, %2;" : "=r"(r) : "r"(a), "r"(cta)); return r; }
__device__ __forceinline__ void st_async(uint32_t a, uint32_t v, uint32_t bar) {
  asm volatile("st.async.weak.shared::cluster.mbarrier::complete_tx::bytes.b32 [%0], %1, [%2];" ::"r"(a), "r"(v), "r"(bar) : "memory");
}
__device__ __forceinline__ void st_async4(uint32_t a, uint32_t x, uint32_t y, uint32_t z, uint32_t w, uint32_t bar) {
  asm volatile("st.async.weak.shared::cluster.mbarrier::complete_tx::bytes.v4.b32 [%0], {%1,%2,%3,%4}, [%5];" ::"r"(a), "r"(x), "r"(y), "r"(z), "r"(w), "r"(bar) : "memory");
}
__device__ __forceinline__ void tma3d_st(const CUtensorMap* m, uint32_t src, int c0, int c1, int c2) {
  asm volatile("cp.async.bulk.tensor.3d.global.shared::cta.bulk_group [%0, {%2, %3, %4}], [%1];" ::"l"(m), "r"(src), "r"(c0), "r"(c1), "r"(c2) : "memory");
}
__device__ __forceinline__ uint4 ld_rlx4(const void* p) {
  uint4 v;
  asm volatile("{\n.reg .b128 t;\n.reg .b64 a, b;\nld.relaxed.gpu.global.b128 t, [%4];\nmov.b128 {a, b}, t;\nmov.b64 {%0, %1}, a;\nmov.b64 {%2, %3}, b;\n}\n"
               : "=r"(v.x), "=r"(v.y), "=r"(v.z), "=r"(v.w) : "l"(p) : "memory");
  return v;
}
__device__ __forceinline__ void ld_stale4(uint4& v, const void* p, uint32_t tag) {
  asm volatile("{\n.reg .b128 t;\n.reg .b64 a, b;\n.reg .b32 x;\n.reg .pred p;\n"
               "lop3.b32 x, %0, %5, 1, 0x28;\nsetp.ne.u32 p, x, 0;\n"
               "mov.b64 a, {%0, %1};\nmov.b64 b, {%2, %3};\nmov.b128 t, {a, b};\n"
               "@p ld.relaxed.gpu.global.b128 t, [%4];\n"
               "mov.b128 {a, b}, t;\nmov.b64 {%0, %1}, a;\nmov.b64 {%2, %3}, b;\n}\n"
               : "+r"(v.x), "+r"(v.y), "+r"(v.z), "+r"(v.w) : "l"(p), "r"(tag) : "memory");
}
__device__ __forceinline__ void st_tag4(void* p, float a, float b, float c, float d, uint32_t tag) {
  asm volatile("{\n.reg .b128 t;\n.reg .b64 a, b;\nmov.b64 a, {%1, %2};\nmov.b64 b, {%3, %4};\nmov.b128 t, {a, b};\nst.relaxed.gpu.global.b128 [%0], t;\n}\n"
               ::"l"(p), "r"((__float_as_uint(a) & ~1u) | tag), "f"(b), "f"(c), "f"(d) : "memory");
}
__device__ __forceinline__ uint32_t stale8(const uint4 (&f)[8], uint32_t tag) {
  uint32_t r[4];
#pragma unroll
  for (int i = 0; i < 4; i++) asm("lop3.b32 %0, %1, %2, %3, 0x7E;" : "=r"(r[i]) : "r"(f[2 * i].x), "r"(f[2 * i + 1].x), "r"(tag));
  asm("lop3.b32 %0, %0, %1, %2, 0xFE;" : "+r"(r[0]) : "r"(r[1]), "r"(r[2]));
  return r[0] | r[3];
}

struct ConvC { uint32_t a1[2][4], wa[2], wb[2], sg; };
__device__ __forceinline__ uint64_t dsc(uint32_t lo, uint32_t hi) { return ((uint64_t)hi << 32) | lo; }
__device__ __forceinline__ uint32_t hfma(uint32_t a, uint32_t b, uint32_t c) { uint32_t r; asm("fma.rn.f16x2 %0, %1, %2, %3;" : "=r"(r) : "r"(a), "r"(b), "r"(c)); return r; }
__device__ __forceinline__ uint32_t hfnma(uint32_t a, uint32_t b, uint32_t c) { uint32_t r; asm("{.reg .b32 n; neg.f16x2 n, %1; fma.rn.f16x2 %0, n, %2, %3;}" : "=r"(r) : "r"(a), "r"(b), "r"(c)); return r; }
__device__ __forceinline__ uint32_t hmul16(uint32_t a, uint32_t b) { uint32_t r; asm("mul.rn.f16x2 %0, %1, %2;" : "=r"(r) : "r"(a), "r"(b)); return r; }
template <int N> __device__ __forceinline__ void keepu(uint32_t (&d)[N]) {
#pragma unroll
  for (int i = 0; i < N; i++) asm volatile("" : "+r"(d[i])::"memory");
}
__device__ __forceinline__ void conv_m1(const ConvC& K, uint32_t (&u)[16], uint32_t l) {
  wg_fence();
  wgmma_hrs_n64<1>(u, K.a1[0][0], K.a1[0][1], K.a1[0][2], K.a1[0][3], dsc(l, 32), 0);
  wgmma_hrs_n64<1>(u, K.a1[1][0], K.a1[1][1], K.a1[1][2], K.a1[1][3], dsc(l + 16, 32), 1);
  wg_commit();
}
__device__ __forceinline__ void conv_s2(const ConvC& K, uint32_t (&u)[16], uint32_t (&Z)[2][8], uint32_t dfl) {
  uint32_t fr[8], fi[8];
#pragma unroll
  for (int c = 0; c < 8; c++) {
    const uint32_t r = hfma(K.wa[c & 1], u[2 * c + 1], u[2 * c]);
    fi[c] = hfma(K.wb[c & 1], r, u[2 * c + 1]);
    fr[c] = hfma(K.wa[c & 1], fi[c], r);
  }
  wg_fence();
#pragma unroll
  for (int p = 0; p < 2; p++) {
    wgmma_hrs_n32<0>(Z[p], fr[4 * p], fr[4 * p + 2], fr[4 * p + 1], fr[4 * p + 3], dsc(dfl, 32), 0);
    wgmma_hrs_n32<0>(Z[p], fi[4 * p], fi[4 * p + 2], fi[4 * p + 1], fi[4 * p + 3], dsc(dfl + 16, 32), 1);
  }
  wg_commit();
}
__device__ __forceinline__ void conv_win(const ConvC& K, const uint32_t (&X)[2][8], uint32_t (&W)[2][8]) {
#pragma unroll
  for (int b = 0; b < 4; b++)
#pragma unroll
    for (int c = 0; c < 2; c++) {
      const uint32_t xr = X[b >> 1][2 * c + (b & 1)], xi = X[b >> 1][4 + 2 * c + (b & 1)];
      const int a = b ? b - 1 : 0;
      W[b >> 1][2 * c + (b & 1)] = b ? hfnma(K.sg, X[a >> 1][4 + 2 * c + (a & 1)], xr) : xr;
      W[b >> 1][4 + 2 * c + (b & 1)] = b ? hfma(K.sg, X[a >> 1][2 * c + (a & 1)], xi) : xi;
    }
}
template <int p>
__device__ __forceinline__ void conv_pw(uint32_t (&X)[2][8], uint32_t (&H)[2][8], uint32_t (&V)[8], uint32_t dil) {
  uint32_t pr[2][2], pi[2][2];
#pragma unroll
  for (int jj = 0; jj < 2; jj++)
#pragma unroll
    for (int c = 0; c < 2; c++) {
      const int j = 2 * p + jj;
      uint32_t sr = 0, si = 0;
#pragma unroll
      for (int a = 0; a <= j; a++) {
        const int b = j - a;
        const uint32_t hr = H[a >> 1][2 * c + (a & 1)], hi = H[a >> 1][4 + 2 * c + (a & 1)];
        const uint32_t xr = X[b >> 1][2 * c + (b & 1)], xi = X[b >> 1][4 + 2 * c + (b & 1)];
        sr = a == 0 ? hmul16(hr, xr) : hfma(hr, xr, sr);
        si = a == 0 ? hmul16(hr, xi) : hfma(hr, xi, si);
        sr = hfnma(hi, xi, sr);
        si = hfma(hi, xr, si);
      }
      pr[jj][c] = sr; pi[jj][c] = si;
    }
  wg_fence();
  wgmma_hrs_n32<0>(V, pr[0][0], pr[1][0], pr[0][1], pr[1][1], dsc(dil, 32), 0);
  wgmma_hrs_n32<0>(V, pi[0][0], pi[1][0], pi[0][1], pi[1][1], dsc(dil + 16, 32), 1);
  wg_commit();
}
template <int p>
__device__ __forceinline__ void conv_it(const ConvC& K, uint32_t (&V)[8], uint32_t vst) {
#pragma unroll
  for (int jj = 0; jj < 2; jj++) {
    uint32_t wr[2], wi[2];
#pragma unroll
    for (int c = 0; c < 2; c++) {
      const uint32_t r = hfnma(K.wa[c], V[4 + 2 * c + jj], V[2 * c + jj]);
      wi[c] = hfnma(K.wb[c], r, V[4 + 2 * c + jj]);
      wr[c] = hfnma(K.wa[c], wi[c], r);
    }
    stsm4(vst + (2 * p + jj) * 2048, wr[0], wr[1], wi[0], wi[1]);
  }
}
__device__ __forceinline__ void conv_m4(uint32_t (&y)[8], uint32_t (&a)[4][4], uint32_t d4l) {
  wg_fence();
  wgmma_hrs_n32<0>(y, a[0][0], a[0][1], a[0][2], a[0][3], dsc(d4l, 64), 0);
#pragma unroll
  for (int s = 1; s < 4; s++) wgmma_hrs_n32<0>(y, a[s][0], a[s][1], a[s][2], a[s][3], dsc(d4l + s * 16, 64), 1);
  wg_commit();
}

struct Params {
  CUtensorMap tmX0, tmW, tmX, tmWo, tmWo1, tmK, tmV, tmQ, tmOA, tmOB;
  const __nv_bfloat16 *shift_k, *h, *D, *x, *w, *wo, *q;
  float *part, *kv;
  uint4* o;
  const uint32_t *thr, *img;
};

__global__ void __cluster_dims__(2, 1, 1) __launch_bounds__(384, 1) fused_kernel(const __grid_constant__ Params P) {
  extern __shared__ __align__(1024) uint8_t smem[];
#define MAP_PF(m) asm volatile("prefetch.tensormap [%0];" ::"l"(&P.m) : "memory")
  if (threadIdx.x == 0) { MAP_PF(tmX0); MAP_PF(tmW); MAP_PF(tmX); }
  const uint32_t sb = __shfl_sync(~0u, smem_u32(smem), 0);
  const uint32_t bars = sb + OFF_BAR;
  const int tid = threadIdx.x, lane = tid & 31;
  const int warp = __shfl_sync(~0u, tid >> 5, 0);
  const int rank = blockIdx.x & 1, pc = blockIdx.x >> 1;
  const unsigned c7 = pc + 6, g7 = (c7 * 37) >> 8;
  const int mb = pc < 4 ? 4 + pc : pc < 36 ? (pc - 4) >> 3 : g7 - 2;
  const int hq = pc < 4 ? 0 : pc < 36 ? (pc - 4) & 7 : 1 + c7 - 7 * g7;
  const int cl = 8 * hq + mb;
  const int hp = 2 * hq + rank;
  const int rb = 2 * mb + (hq >> 2), cb = hq & 3;
#define BAR(i) (bars + 8 * (i))
#define OCNT(rb, hh) ((unsigned*)(P.o + (rb) * OBLK + 16 * 1024 + 8 * (hh)))
#define EPOCH (OCNT(rb, 2)[hp & 7])

  if (tid == 0) { STAMP(0, 0); GSTAMP(0, 30); }
  if (warp == 8) {
    if (elect_one()) {
      mbar_init(BAR(B_FIRST), 1);
      asm volatile("fence.mbarrier_init.release.cluster;" ::: "memory");
      mbar_expect(BAR(B_FIRST), STAGE_BYTES - 16384);
      tma2d(sb, &P.tmX0, 0, mb * 256, BAR(B_FIRST));
      tma2d(sb + 16384, &P.tmX0, 0, mb * 256 + 128, BAR(B_FIRST));
      tma3d(sb + 32768, &P.tmW, hp * 64, 0, 0, BAR(B_FIRST));
      mbar_init(BAR(B_FULL1), 1);
      asm volatile("fence.mbarrier_init.release.cluster;" ::: "memory");
    }
    if (lane == 0) STAMP(3, 21);
  } else if (lane == 0) {
    const int wi = warp - (warp > 8);
#pragma unroll
    for (int r = 0; r < 6; r++)
      if (r < 5 || wi < B_COUNT - 56) mbar_init(BAR(1 + 11 * r + wi), ((uint32_t)(bar_counts(r) >> (4 * wi)) & 15) + 1);
    asm volatile("fence.mbarrier_init.release.cluster;" ::: "memory");
  }
  if (tid == 0) STAMP(2, 6);
  asm volatile("barrier.cluster.arrive.relaxed.aligned;\nbarrier.cluster.wait.aligned;" ::: "memory");
  if (warp == 8 && elect_one()) {
    mbar_expect(BAR(B_FULL1), 16384);
    tma2d_mc(sb + 8192 + rank * 16384, &P.tmX0, 0, mb * 256 + 64 + rank * 128, BAR(B_FULL1));
  }
  if (tid == 256) STAMP(2, 7);

  if (warp < 8) {
    asm volatile("setmaxnreg.inc.sync.aligned.u32 224;");
    const int wg = warp >> 2, w = warp & 3, g = lane >> 2, q = lane & 3, t = tid & 127;
    const bool elect = (t == 0);
    const uint32_t s16 = (sb & 0x3FFFF) >> 4;
    uint32_t pq[2][16], ux[16], uh[16], X[4][2][8], H[4][2][8];
    ConvC K;
    const uint32_t dfl = s16 + (OFF_F2F >> 4) + (8 << 16), dil = s16 + (OFF_F2I >> 4) + (8 << 16), d4l = s16 + (OFF_F4 >> 4) + (8 << 16);
    const uint32_t xl = s16 + (OFF_XT >> 4) + 4 * wg * (XT_STRIDE >> 4) + (8 << 16);
    const uint32_t hl = s16 + (OFF_H >> 4) + wg * 512 + (8 << 16);
    {
      float acc[2][96];
      {
#pragma unroll
        for (int i = 0; i < 192; i++) { acc[i / 96][i % 96] = i % 96 < 64 ? 1.f : 0.f; asm volatile("" : "+f"(acc[i / 96][i % 96])); }
      }
      {
#pragma unroll
        for (int mt = 0; mt < 2; mt++) {
          mbar_wait(BAR(mt ? B_FULL1 : B_FIRST), 0);
          if (mt == 0 && elect) { STAMP(wg, 1); GSTAMP(wg, 26); }
          wg_fence();
#pragma unroll
          for (int ks = 0; ks < 4; ks++)
            wgmma_ss_n192<0, 1>(acc[mt], dsc(s16 + wg * 1024 + mt * 512 + (1 << 16) + ks * 2, SW128), dsc(s16 + 2048 + (512 << 16) + ks * 128, SW128), 1);
        }
        wg_commit();
      }
      int st = 1, ph = 0;
#pragma unroll 1
      for (int kb = 1; kb < 14; kb++) {
        mbar_wait(BAR(B_FULL1 + st), ph);
        if (kb == 8 && elect) { STAMP(wg, 16); GSTAMP(wg, 25); }
        const uint32_t da = s16 + st * (STAGE_BYTES >> 4) + wg * 1024 + (1 << 16);
        const uint32_t db = s16 + st * (STAGE_BYTES >> 4) + 2048 + (512 << 16);
        wg_fence();
#pragma unroll
        for (int ks = 0; ks < 4; ks++) {
          wgmma_ss_n192<0, 1>(acc[0], dsc(da + ks * 2, SW128), dsc(db + ks * 128, SW128), 1);
          wgmma_ss_n192<0, 1>(acc[1], dsc(da + 512 + ks * 2, SW128), dsc(db + ks * 128, SW128), 1);
        }
        wg_commit();
        wg_wait<1>();
        if (t < 2) mbar_arrive_cl(BAR(B_EMPTY1 + (st == 0 ? 2 : st - 1)), t);
        if (++st == 3) { st = 0; ph ^= 1; }
      }
#define TAIL_MMA(mt, stage) do { wg_fence(); _Pragma("unroll") for (int ks = 0; ks < 4; ks++) \
        wgmma_ss_n192<0, 1>(acc[mt], dsc(s16 + (stage) * (STAGE_BYTES >> 4) + wg * 1024 + (mt) * 512 + (1 << 16) + ks * 2, SW128), \
                            dsc(s16 + (stage) * (STAGE_BYTES >> 4) + 2048 + (512 << 16) + ks * 128, SW128), 1); wg_commit(); } while (0)
      mbar_wait(BAR(B_FULL1 + 2), 0);
      TAIL_MMA(0, 2);
      wg_wait<1>();
      if (elect) mbar_arrive(BAR(B_SFREE));
      mbar_wait(BAR(B_FULL1 + 0), 1);
      TAIL_MMA(0, 0);
      TAIL_MMA(1, 2);
      const uint32_t lrow = sb + wg * 16384 + (16 * w + 8 * ((lane >> 3) & 1) + (lane & 7)) * 128 + (((lane >> 4) ^ (lane & 7)) << 4);
#define E1K(mt, i) do { if (opaque_true()) { _Pragma("unroll") for (int j = (i); j < (i) + 2; j++) { \
          const float* a = &acc[mt][32 + 8 * j]; const float* b = a + 32; const uint32_t o = (lrow ^ (j * 32)) + (mt) * 8192; \
          stsm4(o + 2 * STAGE_BYTES, pk2(b[0], b[1]), pk2(b[2], b[3]), pk2(b[4], b[5]), pk2(b[6], b[7])); \
          stsm4(o, phi2(a[0], a[1]), phi2(a[2], a[3]), phi2(a[4], a[5]), phi2(a[6], a[7])); } } } while (0)
#define E1Q(mt) do { if (opaque_true()) { _Pragma("unroll") for (int i = 0; i < 16; i++) pq[mt][i] = phi2(acc[mt][2 * i], acc[mt][2 * i + 1]); } } while (0)
#define LOAD_K() do { const uint4* ct = (const uint4*)P.thr + t; \
        _Pragma("unroll") for (int s = 0; s < 2; s++) { const uint4 u = ld_na4(ct + s * 128); K.a1[s][0] = u.x; K.a1[s][1] = u.y; K.a1[s][2] = u.z; K.a1[s][3] = u.w; } \
        const uint4 u = ld_na4(ct + 2 * 128); K.wa[0] = u.x; K.wa[1] = u.y; K.wb[0] = u.z; K.wb[1] = u.w; \
        K.sg = (lane & 4) ? 0xBC00BC00u : 0x3C003C00u; } while (0)
#define PK_READY(mt) do { fence_async(); __syncwarp(); if (lane == 0) mbar_arrive(BAR(B_PKRDY + (mt))); } while (0)
      wg_wait<1>();
      keep(acc[0]);
      if (elect) STAMP(wg, 18);
      E1K(0, 0);
      TAIL_MMA(1, 0);
      E1K(0, 2);
      if (elect) STAMP(wg, 19);
      PK_READY(0);
      wg_wait<0>();
      keep(acc[1]);
      if (elect) mbar_arrive(BAR(B_G1DONE));
      asm volatile("setmaxnreg.dec.sync.aligned.u32 %0;" ::"n"(RC));
      if (elect) { STAMP(wg, 2); GSTAMP(wg, 27); }
      E1K(1, 0);
      if (elect) STAMP(wg, 20);
      E1K(1, 2);
      if (elect) STAMP(wg, 21);
      PK_READY(1);
      if (elect) STAMP(wg, 3);
      LOAD_K();
      if (elect) STAMP(wg, 4);
      E1Q(0);
      E1Q(1);
      if (elect) STAMP(wg, 17);
      mbar_wait(BAR(B_H), 0);
      conv_m1(K, ux, xl);
      conv_m1(K, uh, hl);
      wg_wait<1>(); keepu(ux);
      if (lane == 0) mbar_arrive_cl(BAR(B_XFREE + 4 * wg), rank ^ 1);
      conv_s2(K, ux, X[0], dfl);
      wg_wait<1>(); keepu(uh);
      conv_s2(K, uh, H[0], dfl);
    }
    if (elect) STAMP(wg, 5);
    float acc[64];
#define G2_MMA(da, db, first) do { wg_fence(); _Pragma("unroll") for (int ks = 0; ks < 4; ks++) \
        wgmma_ss_n128<0, 1>(acc, dsc((da) + ks * 2, SW128), dsc((db) + ks * 128, SW128), ks || !(first)); wg_commit(); } while (0)
    const uint32_t a0 = s16 + wg * 512 + (1 << 16), b0 = s16 + (512 << 16);
    uint32_t cons = mapa(BAR(B_CONS2 - 1 + G2E), t & 1);
    const bool rel = __shfl_sync(~0u, t, lane) < 2;
    {
      uint32_t vst = sb + wg * 8192 + w * 512 + lane * 16, vld = sb + wg * 8192 + w * 2048 + lane * 16;
      uint32_t ya = mapa(sb + OFF_XT + 4 * wg * XT_STRIDE + (2 * rank + (w & 1)) * 1024 + lane * 16, w >> 1);
      const uint32_t ybar = mapa(BAR(B_Y), w >> 1);
      asm volatile("" : "+r"(vst), "+r"(vld), "+r"(ya));
      uint32_t W[2][8], V0[8], V1[8], y[8], a[4][4];
      uint4 ov[4];
      uint4* const ot = P.o + (2 * mb + wg) * OBLK + hq * 1024 + (16 * w + g) * 8 + ((4 * rank + q) ^ g);
#define YOUT(i) do { if ((w >> 1) == rank) { \
          asm volatile("st.shared.v4.b32 [%0], {%1,%2,%3,%4};" ::"r"(ya + (i) * XT_STRIDE), "r"(y[0]), "r"(y[2]), "r"(y[4]), "r"(y[6]) : "memory"); \
          asm volatile("st.shared.v4.b32 [%0], {%1,%2,%3,%4};" ::"r"(ya + (i) * XT_STRIDE + 512), "r"(y[1]), "r"(y[3]), "r"(y[5]), "r"(y[7]) : "memory"); \
        } else { \
          mbar_wait(BAR(B_XFREE + 4 * wg + (i)), 0); \
          st_async4(ya + (i) * XT_STRIDE, y[0], y[2], y[4], y[6], ybar); \
          st_async4(ya + (i) * XT_STRIDE + 512, y[1], y[3], y[5], y[7], ybar); } } while (0)
      auto ocalc = [&](const int hh) {
        if (hh == 0) {
          if (elect) STAMP(wg, 8);
          mbar_wait(BAR(B_KV), 0);
          if (elect) STAMP(wg, 9);
        } else mbar_wait(BAR(B_KV1), 0);
        float oa[2][20];
        wg_fence();
#pragma unroll
        for (int m = 0; m < 4; m++) {
          const uint32_t* p = &pq[m & 1][8 * hh + 4 * (m >> 1)];
          wgmma_rs_n40<1>(oa[m & 1], p[0], p[1], p[2], p[3], dsc(s16 + (OFF_KVB >> 4) + hh * 160 + (m >> 1) * 16 + (8 << 16), 32), m >> 1);
        }
        wg_commit();
        wg_wait<0>();
#pragma unroll
        for (int mt = 0; mt < 2; mt++) {
          float (&o)[20] = oa[mt];
          keep(o);
          const uint32_t den = hadd(pk2(o[16], o[18]), 0x35863586u);
#pragma unroll
          for (int r = 0; r < 2; r++) {
            const float ri = rcp_fast(__uint_as_float(r ? (den & 0xFFFF0000u) : (den << 16)));
            uint4 u;
            u.x = pk2(o[2 * r] * ri, o[2 * r + 1] * ri);
            u.y = pk2(o[4 + 2 * r] * ri, o[5 + 2 * r] * ri);
            u.z = pk2(o[8 + 2 * r] * ri, o[9 + 2 * r] * ri);
            u.w = pk2(o[12 + 2 * r] * ri, o[13 + 2 * r] * ri);
            if (hh == 0) st_cg4(ot + (64 * mt + 8 * r) * 8, u); else ov[2 * mt + r] = u;
          }
        }
        if (hh == 0) {
          __syncwarp();
          if (lane == 0) mbar_arrive(BAR(B_ODONE));
          if (elect) STAMP(wg, 10);
        }
      };
      auto trickle = [&](const int qs) {
        const int m = qs - 2 * (OCH + O1D) - (TRICK - 1);
        if (m >= 0 && m < 4) {
          st_cg4(ot + 8 * 1024 + (64 * (m >> 1) + 8 * (m & 1)) * 8, ov[m]);
          if (m == 3) { __syncwarp(); if (lane == 0) mbar_arrive(BAR(B_ODONE1)); }
        }
      };
#pragma unroll
      for (int i = 0; i < 4; i++) {
        const bool nx = i < 3;
        const int n = nx ? i + 1 : i;
        const uint32_t vo = (i & 1) ? OFF_H + (i >> 1) * 16384 : OFF_VP;
        if (2 * i == OCH) ocalc(0);
        if (2 * i == OCH + O1D) ocalc(1);
        if (nx) {
          conv_m1(K, ux, xl + n * (XT_STRIDE >> 4));
          conv_m1(K, uh, hl + (n >> 1) * 1024 + (n & 1) * 256);
        }
        if (2 * i != OCH && 2 * i != OCH + O1D) { if (nx) { if (i > 0) wg_wait<3>(); else wg_wait<2>(); } else wg_wait<1>(); }
        keepu(X[i][0]); keepu(X[i][1]); keepu(H[i][0]); keepu(H[i][1]);
        conv_win(K, X[i], W);
        trickle(4 * i);
        conv_pw<0>(W, H[i], V0, dil);
        conv_pw<1>(W, H[i], V1, dil);
        trickle(4 * i + 1);
        wg_wait<2>();
        if (i > 0) { keepu(y); YOUT(i - 1); }
        if (2 * i + 1 == OCH) ocalc(0);
        if (2 * i + 1 == OCH + O1D) ocalc(1);
        if (nx) {
          keepu(ux); keepu(uh);
          if (lane == 0) mbar_arrive_cl(BAR(B_XFREE + 4 * wg + n), rank ^ 1);
          conv_s2(K, ux, X[n], dfl);
          wg_wait<1>();
        } else wg_wait<0>();
        keepu(V0); keepu(V1);
        if (G2E && G2P == 0 && i == 3) { mbar_wait(BAR(B_FULL2), 0); G2_MMA(a0 + (SLOT_A & 15) * 1024, b0 + (SLOT_B & 15) * 1024, true); }
        trickle(4 * i + 2);
        if (i == 0) mbar_wait(BAR(B_H2), 0);
        conv_it<0>(K, V0, vst + vo);
        conv_it<1>(K, V1, vst + vo);
        if (G2E && G2P == 1 && i == 3) { mbar_wait(BAR(B_FULL2), 0); G2_MMA(a0 + (SLOT_A & 15) * 1024, b0 + (SLOT_B & 15) * 1024, true); }
        bar_sync(1 + wg);
#pragma unroll
        for (int s = 0; s < 4; s++) ldsm4t(a[s], vld + vo + s * 512);
        if (nx) conv_s2(K, uh, H[n], dfl);
        conv_m4(y, a, d4l);
        trickle(4 * i + 3);
        if (i > 0 && lane < 2) mbar_arrive_cl(BAR(B_AFREE + i - 1), lane);
        if (elect && i < 3) STAMP(wg, i < 2 ? 6 + i : 9 + i);
      }
      if (G2E && G2P == 2) { mbar_wait(BAR(B_FULL2), 0); G2_MMA(a0 + (SLOT_A & 15) * 1024, b0 + (SLOT_B & 15) * 1024, true); wg_wait<1>(); }
      else wg_wait<0>();
      keepu(y);
      if (G2E && G2P < 2 && rel) asm volatile("mbarrier.arrive.shared::cluster.b64 _, [%0];" ::"r"(cons) : "memory");
      YOUT(3);
      __syncwarp();
      if (lane == 0) mbar_arrive(BAR(B_Y));
      if (elect) STAMP(wg, 12);
    }
    {
      uint64_t ta = SLOT_A >> (4 * G2E), tb = SLOT_B >> (4 * G2E);
      uint32_t da = a0 + ((uint32_t)ta & 15) * 1024, db = b0 + ((uint32_t)tb & 15) * 1024, fb = BAR(B_FULL2 + G2E);
#pragma unroll 1
      for (int kb = G2E; kb < HOLD2; kb++) {
        mbar_wait(fb, 0);
        G2_MMA(da, db, kb == 0);
        ta >>= 4; tb >>= 4;
        da = a0 + ((uint32_t)ta & 15) * 1024; db = b0 + ((uint32_t)tb & 15) * 1024; fb += 8;
        asm volatile("" : "+r"(da), "+r"(db));
        wg_wait<1>();
        if ((kb > G2E || (G2E && G2P == 2)) && kb < 12 && rel) asm volatile("mbarrier.arrive.shared::cluster.b64 _, [%0];" ::"r"(cons) : "memory");
        cons += 8;
      }
#pragma unroll
      for (int kb = HOLD2; kb < 16; kb++) {
        if (wg == 1) mbar_wait(BAR(B_FULL2 + kb), 0);
        else if (kb == HOLD2) asm volatile("bar.sync 3, 256;" ::: "memory");
        G2_MMA(a0 + ((SLOT_A >> (4 * kb)) & 15) * 1024, b0 + ((SLOT_B >> (4 * kb)) & 15) * 1024, false);
      }
      if (wg == 1) asm volatile("bar.arrive 3, 256;" ::: "memory");
      const uint32_t stg = sb + wg * 8192 + w * 2048, so0 = ((SLOT_A >> 56) & 15) * 16384, so1 = ((SLOT_A >> 60) & 15) * 16384;
      const uint32_t lrow = stg + (8 * ((lane >> 3) & 1) + (lane & 7)) * 128 + (((lane >> 4) ^ (lane & 7)) << 4);
      const int col = 1024 + 256 * cb + 128 * rank, row = 128 * rb + 64 * wg + 16 * w;
      wg_wait<0>();
      keep(acc);
      if (elect) { STAMP(wg, 14); GSTAMP(wg, 29); }
#pragma unroll
      for (int cp = 0; cp < 8; cp++) {
        const float* a = &acc[8 * cp];
        stsm4((lrow ^ ((cp & 3) * 32)) + (cp >> 2 ? so1 : so0), pk2(a[0], a[1]), pk2(a[2], a[3]), pk2(a[4], a[5]), pk2(a[6], a[7]));
        if ((cp & 3) == 3) {
          fence_async();
          __syncwarp();
          if (elect_one()) tma2d_st(&P.tmOB, stg + (cp >> 2 ? so1 : so0), col + (cp >> 2) * 64, row);
        }
      }
      asm volatile("cp.async.bulk.commit_group;\ncp.async.bulk.wait_group.read 0;" ::: "memory");
      if (elect) {
        STAMP(wg, 15); GSTAMP(wg, 31); PDUMP(wg); if (wg == 0) PDUMP(2);
      }
    }
  } else {
    asm volatile("setmaxnreg.dec.sync.aligned.u32 56;");
    const int hw = warp - 9, g = lane >> 2, q = lane & 3;
#define sbar (bars + 8 * (B_STG - 18) + 16 * warp)
    if (warp == 8) {
      if (D1) __nanosleep(D1);
      int st = 1, pp = 1;
      const uint8_t* pfx = (const uint8_t*)P.x + (mb * 256 + hp * 16 + (lane & 15)) * 2048;
      const uint8_t* pfw = (const uint8_t*)P.w + (mb * 8 + (lane & 7)) * 6144 + (lane >> 3) * 2048 + hp * 128;
#pragma unroll 1
      for (int kb = 1; kb < 16; kb++) {
        if (kb >= 3) mbar_wait(BAR(B_EMPTY1 + st), pp);
        const uint32_t sa = sb + st * STAGE_BYTES;
        if (elect_one()) {
          mbar_expect(BAR(B_FULL1 + st), STAGE_BYTES);
          tma2d_mc(sa + rank * 16384, &P.tmX, kb * 64, mb * 256 + rank * 128, BAR(B_FULL1 + st));
          tma3d(sa + 32768, &P.tmW, hp * 64, kb * 64, 0, BAR(B_FULL1 + st));
        }
        if (kb == 1 && lane == 0) STAMP(2, 24);
        if (PFD && kb >= 2) {
#pragma unroll 1
          for (int j = kb == 2 ? 3 : kb + PFD; j <= kb + PFD && j < 16; j++) {
            if (lane < 16) asm volatile("prefetch.global.L2 [%0];" ::"l"(pfx + j * 128));
            if (lane < 24) asm volatile("prefetch.global.L2 [%0];" ::"l"(pfw + j * (64 * 6144)));
          }
          if (kb >= QPF && kb < QPF + 8) asm volatile("prefetch.global.L2 [%0];" ::"l"((const uint8_t*)P.q + (blockIdx.x * 256 + (kb - QPF) * 32 + lane) * 128));
          if (kb >= 4)
            asm volatile("prefetch.global.L2 [%0];" ::"l"(kb < 12 ? (const uint8_t*)P.h + ((2 * cl + rank) * 256 + (kb - 4) * 32 + lane) * 128
                                                                  : (const uint8_t*)P.wo + (blockIdx.x * 128 + (kb - 12) * 32 + lane) * 128));
        }
        if (++st == 3) { st = 0; pp ^= 1; }
      }
      if (elect_one()) { MAP_PF(tmWo); MAP_PF(tmWo1); }
      if (lane == 0) STAMP(2, 1);
    } else {
      {
        const uint32_t clk0 = __shfl_sync(~0u, (uint32_t)clock(), 0), stg = sb + OFF_STG + hw * STG_STRIDE;
        const unsigned epoch = __shfl_sync(~0u, EPOCH, 0);
        const uint32_t tag = ~epoch & 1;
        uint32_t tap[2][4];
#pragma unroll
        for (int cg = 0; cg < 2; cg++) {
          const uint2 u = __ldg((const uint2*)(P.shift_k + (16 * cl + 8 * cg + g) * 4));
          tap[cg][0] = __byte_perm(u.x, 0, 0x1010); tap[cg][1] = __byte_perm(u.x, 0, 0x3232);
          tap[cg][2] = __byte_perm(u.y, 0, 0x1010); tap[cg][3] = __byte_perm(u.y, 0, 0x3232);
        }
        if (hw == 0 && lane < 8) *(float*)(smem + OFF_D + 4 * lane) = __bfloat162float(P.D[16 * cl + 8 * rank + lane]);
        if (hw == 1 && lane < 24) asm volatile("prefetch.global.L2 [%0];" ::"l"(P.thr + (lane + 24 * rank) * 32));
        if (hw == 0 && elect_one()) {
          *(volatile unsigned*)(smem + OFF_EPOCH) = epoch;
          mbar_expect(BAR(B_XRAW), 16384);
          mbar_expect(BAR(B_Y), 16384 + 64);
        }
#pragma unroll 1
        for (int i = hw * 32 + lane; i < 528; i += 96) st_tag4(P.part + (hp * 8 + mb) * 2176 + 4 * i, 0.f, 0.f, 0.f, 0.f, tag ^ 1);
        if (hw < 2 || lane < 2) st_tag4(P.kv + hp * 2176 + (4 * (hw < 2 ? 64 * mb + 32 * hw + lane : 512 + 8 * (mb & 1) + (mb & 6) + lane)), 0.f, 0.f, 0.f, 0.f, tag ^ 1);
        if (lane == 0) STAMP(3, hw);
        const uint32_t xo = sb + OFF_XT + g * XT_STRIDE + rank * 2048 + q * 4;
        const int krow = 8 + (lane & 7) - (lane >> 3);
        const uint32_t ka = stg + krow * 32 + ((krow & 4) << 2), va = stg + 2304 + lane * 32 + ((lane & 4) << 2);
        int ph = 0, b = 0;
#pragma unroll 1
        for (int ci = hw - 3; ci < 16; ci += 3) {
          const uint32_t bo = b ? OFF_F2F - OFF_STG : 0, bn = b ? 0 : OFF_F2F - OFF_STG;
          if (ci + 3 < 16) {
            while (__any_sync(~0u, (uint32_t)clock() - clk0 < HSTART + (ci + 3) * PACE)) __nanosleep(64);
            if (elect_one()) {
              mbar_expect(sbar + 8 * (b ^ 1), 2304 + 2048);
              tma2d(stg + bn, &P.tmK, 16 * cl, 1024 * rank + 64 * (ci + 3) - 8, sbar + 8 * (b ^ 1));
              tma2d(stg + bn + 2304, &P.tmV, 16 * cl, 1024 * rank + 64 * (ci + 3), sbar + 8 * (b ^ 1));
            }
          }
          if (ci >= 0) {
            mbar_wait(sbar + 8 * b, (ph >> b) & 1);
            ph ^= 1 << b;
#pragma unroll 1
            for (int grp = 0; grp < 2; grp++) {
#pragma unroll
              for (int cg = 0; cg < 2; cg++) {
                const uint32_t dst = mapa(xo + (ci >> 3) * 1024 + ((ci & 7) * 4 + 2 * grp) * 16, cg), xbar = mapa(BAR(B_XRAW), cg);
                uint32_t vv[4], kk[4][4];
                ldsm4t(vv, (va ^ (cg * 16)) + bo + grp * 1024);
#pragma unroll
                for (int rg = 0; rg < 4; rg++) ldsm4t(kk[rg], (ka ^ (cg * 16)) + bo + grp * 1024 + rg * 256);
#pragma unroll
                for (int rg = 0; rg < 4; rg++)
                  vv[rg] = hmul(hadd(hadd(hadd(hmul(kk[rg][3], tap[cg][3]), hmul(kk[rg][2], tap[cg][2])), hmul(kk[rg][1], tap[cg][1])), hmul(kk[rg][0], tap[cg][0])), vv[rg]);
                if (cg == rank) {
#pragma unroll
                  for (int rg = 0; rg < 4; rg++) asm volatile("st.shared.b32 [%0], %1;" ::"r"(dst + (rg & 1) * 512 + (rg >> 1) * 16), "r"(vv[rg]) : "memory");
                } else {
#pragma unroll
                  for (int rg = 0; rg < 4; rg++) st_async(dst + (rg & 1) * 512 + (rg >> 1) * 16, vv[rg], xbar);
                }
              }
            }
          }
          b ^= 1;
        }
      }
      if (lane == 0 && hw == 0) STAMP(3, 3);
      asm volatile("bar.sync 4, 96;" ::: "memory");
      if (hw == 0 && elect_one()) { mbar_expect(BAR(B_XT), 10240); bulk_ld(sb + OFF_F2F, P.img, 10240, BAR(B_XT)); }
      mbar_wait(BAR(B_XRAW), 0);
    }
    int e1 = 0;
#pragma unroll 1
    for (int n = hw < 0 ? 3 : 0; n < 4; n++) {
      const bool isH = n >= 3;
      const int c = isH ? (warp & 1) + 2 * (warp & 2) : hw + 3 * n;
      if (c < 8) {
        int ln;
        asm volatile("mov.u32 %0, %%laneid;" : "=r"(ln));
        uint8_t* dst = smem + (isH ? OFF_H + (c & 2) * 8192 + (c >> 2) * 8192 + (c & 1) * 4096 : OFF_XT + c * XT_STRIDE) + ((ln >> 4) * 512 + (ln & 15) * 16);
        const uint8_t* src0 = isH ? (const uint8_t*)P.h + (16 * cl + 8 * rank + c) * 4096 + ((ln & 15) * 32 + (ln & 16)) : dst;
        const uint8_t* src1 = src0 + (isH ? 512 : 256);
        uint32_t v[32];
#pragma unroll
        for (int i = 0; i < 8; i++) {
          const uint4 u = *(const uint4*)(((i & 1) ? src1 : src0) + (i >> 1) * 1024);
          v[4 * i] = u.x; v[4 * i + 1] = u.y; v[4 * i + 2] = u.z; v[4 * i + 3] = u.w;
        }
        if (isH) mbar_wait(BAR(B_XT), 0);
        const float f0 = __uint_as_float(v[0] << 16) + ((isH && ln == 0) ? *(const float*)(smem + OFF_D + 4 * c) : 0.f);
        const int e = norm_exp(v, f0);
        norm_cvt(v, f0, e);
        if (isH) mbar_wait(BAR(B_SFREE), 0);
        else if (ln == 0) smem[OFF_EX + c] = e;
        e1 = e;
#pragma unroll
        for (int i = 0; i < 8; i++)
          *(uint4*)(dst + (i >> 1) * 1024 + (i & 1) * 256) = make_uint4(v[4 * i], v[4 * i + 1], v[4 * i + 2], v[4 * i + 3]);
        if (n < 2 && elect_one()) {
          if (n == 0) mbar_expect(sbar, 4096);
          tma3d(sb + OFF_STG + 2048 * c, &P.tmQ, 16 * cl, 64 * rank, 2 * c, sbar);
        }
      }
      if (n >= 2) {
        fence_async();
        __syncwarp();
        if (lane == 0) { mbar_arrive(BAR(isH ? B_H : B_XT)); STAMP(3, (isH ? 17 : 13) + hw); }
      }
    }
#define SLOT(tab, kb) (sb + ((uint32_t)((tab) >> (4 * (kb))) & 15) * 16384)
#define KT(kb) (!OLOC ? (kb) : (kb) == 0 ? hq : (kb) == hq ? 0 : (kb))
#define LOAD_B(kb) tma4d(SLOT(SLOT_B, kb), &P.tmWo, 0, ((kb) >> 3) * 32, 2 * (KT(kb) & 7), 4 * cb + 2 * rank, BAR(B_FULL2 + (kb)))
#define LOAD_A(kb) bulk_ld_mc(SLOT(SLOT_A, kb) + rank * 8192, P.o + rb * OBLK + KT(kb) * 1024 + rank * 512, 8192, BAR(B_FULL2 + (kb)))
    asm volatile("setmaxnreg.inc.sync.aligned.u32 %0;" ::"n"(504 - 2 * RC));
    {
    int tid;
    asm volatile("mov.u32 %0, %%tid.x;" : "=r"(tid));
    const int lane = tid & 31, g = lane >> 2, q = lane & 3;
    const unsigned epoch = *(volatile unsigned*)(smem + OFF_EPOCH);
    const uint32_t tag = ~epoch & 1;
    const int pi = hw < 2 ? 64 * mb - 288 + tid : 512 + 8 * (mb & 1) + (mb & 6) + (lane & 1);
    const float* psrc = P.part + hp * 8 * 2176 + 4 * pi;
    uint4 f[8];
    {
      const uint32_t s16 = (sb & 0x3FFFF) >> 4;
      const int t = tid & 127, c = 2 + (warp & 1) + 2 * (warp & 2);
      const uint4* hp4 = (const uint4*)(P.h + (16 * cl + 8 * rank + c) * 2048) + ((lane & 15) * 2 + (lane >> 4));
      uint32_t v[32];
#pragma unroll
      for (int i = 0; i < 8; i++) { const uint4 u = ld_na4(hp4 + i * 32); v[4 * i] = u.x; v[4 * i + 1] = u.y; v[4 * i + 2] = u.z; v[4 * i + 3] = u.w; }
      float kva[36];
#pragma unroll
      for (int mt = 0; mt < 2; mt++) {
        mbar_wait(BAR(B_PKRDY + mt), 0);
        wg_fence();
#pragma unroll
        for (int ks = 0; ks < 8; ks++) {
          const uint32_t o = (ks >> 2) * 1024 + mt * 512 + (ks & 3) * 128, vb = (2 * STAGE_BYTES >> 4) + o;
          wgmma_ss_n72<1, 1>(kva, dsc(s16 + o + (1 << 16), SW128), dsc(s16 + vb + (((OFF_ONES >> 4) - vb) << 16), SW128), (mt | ks) != 0);
        }
        wg_commit();
        if (mt == 0 && hw < 0) {
          mbar_wait(BAR(B_G1DONE), 0);
          if (elect_one()) {
#pragma unroll
            for (int kb = 0; kb < BEARLY; kb++) { mbar_expect(BAR(B_FULL2 + kb), 16384); LOAD_B(kb); }
          }
        }
      }
      float* pdst = P.part + (hp * 8 + mb) * 2176 + t * 4;
      float* zdst = P.part + (hp * 8 + mb) * 2176 + 2048 + (t >> 1);
      asm volatile("" : "+l"(pdst), "+l"(zdst));
      wg_wait<0>();
      keep(kva);
      if (hw < 1) {
#pragma unroll
        for (int c = 0; c < 4; c++) st_tag4(pdst + c * 512, kva[4 * c], kva[4 * c + 1], kva[4 * c + 2], kva[4 * c + 3], tag);
      } else {
#pragma unroll
        for (int c = 4; c < 8; c++) st_tag4(pdst + (c - 4) * 512, kva[4 * c], kva[4 * c + 1], kva[4 * c + 2], kva[4 * c + 3], tag);
      }
      const float z2 = __shfl_down_sync(~0u, kva[32], 4), z3 = __shfl_down_sync(~0u, kva[34], 4);
      if (!(lane & 7)) st_tag4(zdst, kva[32], kva[34], z2, z3, tag);
      if (lane == 0) mbar_arrive(BAR(B_PKFREE));
      const uint32_t cst = clock();
      if (hw == 0 && lane == 0) STAMP(3, 24);
      const float f0 = __uint_as_float(v[0] << 16) + (lane == 0 ? *(const float*)(smem + OFF_D + 4 * c) : 0.f);
      const int e = norm_exp(v, f0);
      norm_cvt(v, f0, e);
      if (hw >= 0) {
        while (__any_sync(~0u, (uint32_t)clock() - cst < PD1)) __nanosleep(20);
        if (hw == 0 && lane == 0) STAMP(3, 20);
#pragma unroll
        for (int p = 0; p < 8; p++) f[p] = ld_rlx4(psrc + p * 2176);
      }
      uint8_t* dst = smem + OFF_H + 16384 + (warp & 3) * 4096 + (lane >> 4) * 512 + (lane & 15) * 16;
#pragma unroll
      for (int i = 0; i < 8; i++)
        *(uint4*)(dst + (i >> 1) * 1024 + (i & 1) * 256) = make_uint4(v[4 * i], v[4 * i + 1], v[4 * i + 2], v[4 * i + 3]);
      if (lane < 4) {
        const int cc = c - (lane & 2);
        st_async(mapa(sb + OFF_SCALE + (8 * rank + cc) * 4, lane & 1), min(max(((lane & 2) ? e1 : e) + smem[OFF_EX + cc] - 124, 1), 254) << 23, mapa(BAR(B_Y), lane & 1));
      }
    }
#define H2_READY() do { fence_async(); __syncwarp(); if (lane == 0) mbar_arrive(BAR(B_H2)); } while (0)
    if (warp == 8) {
      H2_READY();
      mbar_wait(BAR(B_PKFREE), 0);
      {
        const uint32_t c0 = clock();
#pragma unroll 1
        for (int i = 0; i < 2 * NPRE - 2 * BEARLY; i++) {
          const int kb = (i >> 1) + BEARLY;
          while (__any_sync(~0u, (uint32_t)clock() - c0 < i * BPACE)) __nanosleep(32);
          if (elect_one()) {
            if (!(i & 1)) mbar_expect(BAR(B_FULL2 + kb), 16384);
            tma4d(SLOT(SLOT_B, kb) + (i & 1) * 8192, &P.tmWo1, 0, 0, 2 * KT(kb), 4 * cb + 2 * rank + (i & 1), BAR(B_FULL2 + kb));
            if (i == 0) mbar_expect(BAR(B_Q), 8192);
            if (i < 4) tma3d(sb + OFF_SPARE + 2048 * i, &P.tmQ, 16 * cl, 64 * rank + 32 * (i >> 1), 2 * ((i + 6) & 7), BAR(B_Q));
          }
        }
      }
      if (elect_one()) { MAP_PF(tmOA); MAP_PF(tmOB); }
      if (lane == 0) STAMP(2, 2);
      if (OLOC) {
        if (elect_one()) mbar_expect(BAR(B_FULL2), 16384);
        mbar_wait(BAR(B_OLOC), 0);
        asm volatile("fence.acquire.cluster;\nfence.proxy.async.global;" ::: "memory");
        if (elect_one()) LOAD_A(0);
      }
      mbar_wait(BAR(B_AFREE), 0);
      if (elect_one()) mbar_expect(BAR(B_FULL2 + OLOC), 16384);
      {
        const uint32_t dst = SLOT(SLOT_A, OLOC) + rank * 8192;
        const uint4* src = P.o + rb * OBLK + KT(OLOC) * 1024 + rank * 512;
        poll_ge(OCNT(rb, 0), 16 * (epoch + 1));
        asm volatile("fence.proxy.async.global;" ::: "memory");
        if (lane == 0) STAMP(2, 3);
        if (elect_one()) bulk_ld_mc(dst, src, 8192, BAR(B_FULL2 + OLOC));
        if (lane == 0) STAMP(3, 23);
      }
#pragma unroll 1
      for (int kb = 1 + OLOC; kb < NPRE; kb++) {
        mbar_wait(BAR(kb < 4 ? B_AFREE + kb - 1 : B_CONS2), 0);
        if (elect_one()) { mbar_expect(BAR(B_FULL2 + kb), 16384); LOAD_A(kb); }
      }
#pragma unroll 1
      for (int kb = NPRE; kb < 16; kb++) {
        mbar_wait(BAR(B_CONS2 + kb - 5), 0);
        if (kb == 8) mbar_wait(BAR(B_O1RDY), 0);
        if (elect_one()) { mbar_expect(BAR(B_FULL2 + kb), 32768); LOAD_A(kb); LOAD_B(kb); }
      }
      if (lane == 0) { EPOCH = epoch + 1; STAMP(2, 5); }
    } else {
      {
#pragma unroll 1
        for (int n = 0; __any_sync(~0u, stale8(f, tag) & 1); n++) {
#pragma unroll
          for (int p = 0; p < 8; p++) ld_stale4(f[p], psrc + p * 2176, tag);
          if (n > SPIN_LIMIT) __trap();
        }
        float s0 = 0.f, s1 = 0.f, s2 = 0.f, s3 = 0.f;
#pragma unroll
        for (int p = 0; p < 8; p++) { s0 += __uint_as_float(f[p].x); s1 += __uint_as_float(f[p].y); s2 += __uint_as_float(f[p].z); s3 += __uint_as_float(f[p].w); }
        if (hw < 2 || lane < 2) st_tag4(P.kv + hp * 2176 + (4 * pi), s0, s1, s2, s3, tag);
      }
      const uint32_t cs2 = clock();
      if (lane == 0 && hw == 0) STAMP(3, 8);
      H2_READY();
      if (hw == 2) {
        unsigned* cnt = OCNT(2 * mb + lane, 0);
#pragma unroll 1
        for (int hh = 0; hh < 2; hh++) {
          mbar_wait(BAR(hh ? B_ODONE1 : B_ODONE), 0);
          if (lane < 2) asm volatile("red.release.gpu.global.add.u32 [%0], 1;" ::"l"(cnt) : "memory");
          if (OLOC && hh == 0 && lane < 2) mbar_arrive_cl(BAR(B_OLOC), lane);
          cnt += 32;
          if (lane == 0) STAMP(3, hh ? 6 : 7);
        }
        poll_ge(OCNT(rb, 1), 16 * (epoch + 1));
        asm volatile("fence.proxy.async.global;" ::: "memory");
        if (lane == 0) { mbar_arrive(BAR(B_O1RDY)); STAMP(2, 4); }
        __syncwarp();
      } else {
        const int t = tid - 288;
        const float* src = P.kv + hp * 2176 + 4 * (t + 32 * hw);
        const float* zsrc = P.kv + hp * 2176 + (2048 + (t & 48) + 2 * (lane & 6));
        mbar_wait(BAR(B_PKFREE), 0);
        while (__any_sync(~0u, (uint32_t)clock() - cs2 < PD2)) __nanosleep(20);
        uint4 zp = ld_rlx4(zsrc);
#pragma unroll
        for (int p = 0; p < 8; p++) f[p] = ld_rlx4(src + 4 * ((p & 3) * 128 + (p >> 2) * 32));
        if (!opaque_true()) __trap();
#pragma unroll 1
        for (int n = 0; __any_sync(~0u, (stale8(f, tag) | (zp.x ^ tag)) & 1); n++) {
          ld_stale4(zp, zsrc, tag);
#pragma unroll
          for (int p = 0; p < 8; p++) ld_stale4(f[p], src + 4 * ((p & 3) * 128 + (p >> 2) * 32), tag);
          if (n > SPIN_LIMIT) __trap();
        }
#define PK2U(a, b) pk2(__uint_as_float(a), __uint_as_float(b))
        const uint32_t zf = (lane & 1) ? ((lane & 8) ? zp.w : zp.z) : ((lane & 8) ? zp.y : zp.x);
        const uint32_t zz = PK2U(zf, zf);
        *(uint4*)(smem + OFF_KVB + hw * 2560 + 2048 + lane * 16) = make_uint4(zz, zz, zz, zz);
#pragma unroll
        for (int hh = 0; hh < 2; hh++) {
          const uint4* ff = &f[4 * hh];
          uint8_t* dst = smem + OFF_KVB + hw * 2560 + q * 512 + (16 * hh + g) * 16;
          *(uint4*)dst = make_uint4(PK2U(ff[0].x, ff[0].y), PK2U(ff[1].x, ff[1].y), PK2U(ff[2].x, ff[2].y), PK2U(ff[3].x, ff[3].y));
          *(uint4*)(dst + 128) = make_uint4(PK2U(ff[0].z, ff[0].w), PK2U(ff[1].z, ff[1].w), PK2U(ff[2].z, ff[2].w), PK2U(ff[3].z, ff[3].w));
        }
        fence_async();
        __syncwarp();
        if (lane == 0) { mbar_arrive(BAR(hw ? B_KV1 : B_KV)); if (hw == 0) STAMP(3, 9); }
      }
#define QBUF(ci) (sb + 2048 * (ci) + ((ci) < 6 ? OFF_STG : (ci) < 10 ? OFF_SPARE - 6 * 2048 : OFF_F2F - 10 * 2048))
      mbar_wait(BAR(B_Y), 0);
      if (elect_one()) {
        mbar_expect(sbar + 8, 4096);
#pragma unroll 1
        for (int ci = hw ? hw + 9 : 12; ci < 16; ci += 3) tma3d(QBUF(ci), &P.tmQ, 16 * cl, 64 * rank + 32, 2 * (ci & 7), sbar + 8);
      }
      mbar_wait(BAR(B_Q), 0);
      mbar_wait(sbar, hw == 0);
      {
        const uint2 f0 = *(const uint2*)(smem + OFF_SCALE + 8 * q), f1 = *(const uint2*)(smem + OFF_SCALE + 32 + 8 * q);
        const uint32_t sc0 = __byte_perm(f0.x, f0.y, 0x7632), sc1 = __byte_perm(f1.x, f1.y, 0x7632);
        const uint32_t yl = sb + OFF_XT + (lane & 7) * XT_STRIDE + (lane >> 3) * 16;
#pragma unroll 1
        for (int ci = hw; ci < 16; ci += 3) {
          const uint32_t qb = QBUF(ci);
          if (ci >= 10) mbar_wait(sbar + 8, 1);
          uint32_t yy[4][4], qq[4][4];
          const uint32_t qa = qb + lane * 32 + ((lane & 4) << 2);
#pragma unroll
          for (int u = 0; u < 4; u++) {
            ldsm4t(yy[u], yl + (u & 1) * 2048 + (2 * ci + (u >> 1)) * 64);
            ldsm4(qq[u], (qa ^ ((u & 1) * 16)) + (u >> 1) * 1024);
          }
          if (!opaque_true()) __trap();
#pragma unroll
          for (int u = 0; u < 4; u++) {
#pragma unroll
            for (int m = 0; m < 4; m++) {
              const float2 f = __half22float2(*(const __half2*)&yy[u][m]);
              qq[u][m] = hmul(qq[u][m], hmul(pk2(f.x, f.y), (u & 1) ? sc1 : sc0));
            }
            stsm4((qa ^ ((u & 1) * 16)) + (u >> 1) * 1024, qq[u][0], qq[u][1], qq[u][2], qq[u][3]);
          }
          fence_async();
          __syncwarp();
          if (elect_one()) tma3d_st(&P.tmOA, qb, 16 * cl, 64 * rank + 32 * (ci >> 3), 2 * (ci & 7));
        }
        asm volatile("cp.async.bulk.commit_group;\ncp.async.bulk.wait_group.read 0;" ::: "memory");
      }
      if (lane == 0) STAMP(3, 10 + hw);
    }
    }
  }
}

typedef CUresult (*EncodeFn)(CUtensorMap*, CUtensorMapDataType, cuuint32_t, void*, const cuuint64_t*, const cuuint64_t*,
                             const cuuint32_t*, const cuuint32_t*, CUtensorMapInterleave, CUtensorMapSwizzle,
                             CUtensorMapL2promotion, CUtensorMapFloatOOBfill);

static void enc(EncodeFn fn, CUtensorMap* m, const void* p, int rank, const cuuint64_t* dims, const cuuint64_t* strides,
                const cuuint32_t* box, CUtensorMapSwizzle swz, CUtensorMapL2promotion promo) {
  cuuint32_t es[4] = {1, 1, 1, 1};
  fn(m, CU_TENSOR_MAP_DATA_TYPE_BFLOAT16, rank, (void*)p, dims, strides, box, es, CU_TENSOR_MAP_INTERLEAVE_NONE, swz, promo,
     CU_TENSOR_MAP_FLOAT_OOB_FILL_NONE);
}

extern "C" void kernel_launch(void* const* d_in, const int* in_sizes, int n_in, void* d_out, int out_size) {
  void* fp = nullptr;
  cudaDriverEntryPointQueryResult qr;
  cudaGetDriverEntryPoint("cuTensorMapEncodeTiled", &fp, cudaEnableDefault, &qr);
  EncodeFn fn = (EncodeFn)fp;
  Params P;
  P.shift_k = (const __nv_bfloat16*)d_in[3]; P.h = (const __nv_bfloat16*)d_in[4]; P.D = (const __nv_bfloat16*)d_in[5];
  P.q = (const __nv_bfloat16*)d_in[0];
  cudaGetSymbolAddress((void**)&P.part, g_part); cudaGetSymbolAddress((void**)&P.kv, g_kv); cudaGetSymbolAddress((void**)&P.o, g_o);
  cudaGetSymbolAddress((void**)&P.thr, c_thr); cudaGetSymbolAddress((void**)&P.img, c_img);
  P.x = (const __nv_bfloat16*)d_in[6]; P.w = (const __nv_bfloat16*)d_in[7]; P.wo = (const __nv_bfloat16*)d_in[8];
  const CUtensorMapSwizzle S128 = CU_TENSOR_MAP_SWIZZLE_128B, S32 = CU_TENSOR_MAP_SWIZZLE_32B;
  const CUtensorMapL2promotion P0 = CU_TENSOR_MAP_L2_PROMOTION_NONE, P128 = CU_TENSOR_MAP_L2_PROMOTION_L2_128B;
  { cuuint64_t d[2] = {1024, 2048}, s[1] = {2048}; cuuint32_t b[2] = {64, 128}; enc(fn, &P.tmX, d_in[6], 2, d, s, b, S128, P128); }
  { cuuint64_t d[2] = {1024, 2048}, s[1] = {2048}; cuuint32_t b[2] = {64, 64}; enc(fn, &P.tmX0, d_in[6], 2, d, s, b, S128, P128); }
  { cuuint64_t d[3] = {1024, 1024, 3}, s[2] = {6144, 2048}; cuuint32_t b[3] = {64, 64, 3}; enc(fn, &P.tmW, d_in[7], 3, d, s, b, S128, P128); }
  { cuuint64_t d[4] = {64, 64, 16, 16}, s[3] = {2048, 131072, 128}; cuuint32_t b[4] = {64, 32, 2, 2}; enc(fn, &P.tmWo, d_in[8], 4, d, s, b, S128, P128); }
  { cuuint64_t d[4] = {64, 64, 16, 16}, s[3] = {2048, 131072, 128}; cuuint32_t b[4] = {64, 32, 2, 1}; enc(fn, &P.tmWo1, d_in[8], 4, d, s, b, S128, P128); }
  { cuuint64_t d[2] = {1024, 2048}, s[1] = {2048}; cuuint32_t b[2] = {16, 72}; enc(fn, &P.tmK, d_in[1], 2, d, s, b, S32, P128); }
  { cuuint64_t d[2] = {1024, 2048}, s[1] = {2048}; cuuint32_t b[2] = {16, 64}; enc(fn, &P.tmV, d_in[2], 2, d, s, b, S32, P128); }
  { cuuint64_t d[3] = {1024, 128, 16}, s[2] = {32768, 2048}; cuuint32_t b[3] = {16, 32, 2}; enc(fn, &P.tmQ, d_in[0], 3, d, s, b, S32, P128); }
  { cuuint64_t d[3] = {1024, 128, 16}, s[2] = {65536, 4096}; cuuint32_t b[3] = {16, 32, 2}; enc(fn, &P.tmOA, d_out, 3, d, s, b, S32, P0); }
  { cuuint64_t d[2] = {2048, 2048}, s[1] = {4096}; cuuint32_t b[2] = {64, 16}; enc(fn, &P.tmOB, d_out, 2, d, s, b, S128, P0); }
  cudaFuncSetAttribute(fused_kernel, cudaFuncAttributeMaxDynamicSharedMemorySize, SMEM_TOTAL);
  fused_kernel<<<128, 384, SMEM_TOTAL>>>(P);
}
```

```cpp
#include <cuda_runtime.h>
#include <cuda_bf16.h>
#include <cuda_fp16.h>
#include <cuda.h>
#include <stdint.h>

template<int TA, int TB, int SA=1> __device__ __forceinline__ void wgmma_ss_n192(float (&d)[96], uint64_t da, uint64_t db, int scale_d) {
  asm volatile("{\n.reg .pred p;\nsetp.ne.b32 p, %98, 0;\n"
    "wgmma.mma_async.sync.aligned.m64n192k16.f32.bf16.bf16 {%0, %1, %2, %3, %4, %5, %6, %7, %8, %9, %10, %11, %12, %13, %14, %15, %16, %17, %18, %19, %20, %21, %22, %23, %24, %25, %26, %27, %28, %29, %30, %31, %32, %33, %34, %35, %36, %37, %38, %39, %40, %41, %42, %43, %44, %45, %46, %47, %48, %49, %50, %51, %52, %53, %54, %55, %56, %57, %58, %59, %60, %61, %62, %63, %64, %65, %66, %67, %68, %69, %70, %71, %72, %73, %74, %75, %76, %77, %78, %79, %80, %81, %82, %83, %84, %85, %86, %87, %88, %89, %90, %91, %92, %93, %94, %95}, %96, %97, p, %101, 1, %99, %100;\n}\n"
    : "+f"(d[0]), "+f"(d[1]), "+f"(d[2]), "+f"(d[3]), "+f"(d[4]), "+f"(d[5]), "+f"(d[6]), "+f"(d[7]), "+f"(d[8]), "+f"(d[9]), "+f"(d[10]), "+f"(d[11]), "+f"(d[12]), "+f"(d[13]), "+f"(d[14]), "+f"(d[15]), "+f"(d[16]), "+f"(d[17]), "+f"(d[18]), "+f"(d[19]), "+f"(d[20]), "+f"(d[21]), "+f"(d[22]), "+f"(d[23]), "+f"(d[24]), "+f"(d[25]), "+f"(d[26]), "+f"(d[27]), "+f"(d[28]), "+f"(d[29]), "+f"(d[30]), "+f"(d[31]), "+f"(d[32]), "+f"(d[33]), "+f"(d[34]), "+f"(d[35]), "+f"(d[36]), "+f"(d[37]), "+f"(d[38]), "+f"(d[39]), "+f"(d[40]), "+f"(d[41]), "+f"(d[42]), "+f"(d[43]), "+f"(d[44]), "+f"(d[45]), "+f"(d[46]), "+f"(d[47]), "+f"(d[48]), "+f"(d[49]), "+f"(d[50]), "+f"(d[51]), "+f"(d[52]), "+f"(d[53]), "+f"(d[54]), "+f"(d[55]), "+f"(d[56]), "+f"(d[57]), "+f"(d[58]), "+f"(d[59]), "+f"(d[60]), "+f"(d[61]), "+f"(d[62]), "+f"(d[63]), "+f"(d[64]), "+f"(d[65]), "+f"(d[66]), "+f"(d[67]), "+f"(d[68]), "+f"(d[69]), "+f"(d[70]), "+f"(d[71]), "+f"(d[72]), "+f"(d[73]), "+f"(d[74]), "+f"(d[75]), "+f"(d[76]), "+f"(d[77]), "+f"(d[78]), "+f"(d[79]), "+f"(d[80]), "+f"(d[81]), "+f"(d[82]), "+f"(d[83]), "+f"(d[84]), "+f"(d[85]), "+f"(d[86]), "+f"(d[87]), "+f"(d[88]), "+f"(d[89]), "+f"(d[90]), "+f"(d[91]), "+f"(d[92]), "+f"(d[93]), "+f"(d[94]), "+f"(d[95])
    : "l"(da), "l"(db), "r"(scale_d), "n"(TA), "n"(TB), "n"(SA));
}
template<int TA, int TB, int SA=1> __device__ __forceinline__ void wgmma_ss_n128(float (&d)[64], uint64_t da, uint64_t db, int scale_d) {
  asm volatile("{\n.reg .pred p;\nsetp.ne.b32 p, %66, 0;\n"
    "wgmma.mma_async.sync.aligned.m64n128k16.f32.bf16.bf16 {%0, %1, %2, %3, %4, %5, %6, %7, %8, %9, %10, %11, %12, %13, %14, %15, %16, %17, %18, %19, %20, %21, %22, %23, %24, %25, %26, %27, %28, %29, %30, %31, %32, %33, %34, %35, %36, %37, %38, %39, %40, %41, %42, %43, %44, %45, %46, %47, %48, %49, %50, %51, %52, %53, %54, %55, %56, %57, %58, %59, %60, %61, %62, %63}, %64, %65, p, %69, 1, %67, %68;\n}\n"
    : "+f"(d[0]), "+f"(d[1]), "+f"(d[2]), "+f"(d[3]), "+f"(d[4]), "+f"(d[5]), "+f"(d[6]), "+f"(d[7]), "+f"(d[8]), "+f"(d[9]), "+f"(d[10]), "+f"(d[11]), "+f"(d[12]), "+f"(d[13]), "+f"(d[14]), "+f"(d[15]), "+f"(d[16]), "+f"(d[17]), "+f"(d[18]), "+f"(d[19]), "+f"(d[20]), "+f"(d[21]), "+f"(d[22]), "+f"(d[23]), "+f"(d[24]), "+f"(d[25]), "+f"(d[26]), "+f"(d[27]), "+f"(d[28]), "+f"(d[29]), "+f"(d[30]), "+f"(d[31]), "+f"(d[32]), "+f"(d[33]), "+f"(d[34]), "+f"(d[35]), "+f"(d[36]), "+f"(d[37]), "+f"(d[38]), "+f"(d[39]), "+f"(d[40]), "+f"(d[41]), "+f"(d[42]), "+f"(d[43]), "+f"(d[44]), "+f"(d[45]), "+f"(d[46]), "+f"(d[47]), "+f"(d[48]), "+f"(d[49]), "+f"(d[50]), "+f"(d[51]), "+f"(d[52]), "+f"(d[53]), "+f"(d[54]), "+f"(d[55]), "+f"(d[56]), "+f"(d[57]), "+f"(d[58]), "+f"(d[59]), "+f"(d[60]), "+f"(d[61]), "+f"(d[62]), "+f"(d[63])
    : "l"(da), "l"(db), "r"(scale_d), "n"(TA), "n"(TB), "n"(SA));
}
template<int TA, int TB, int SA=1> __device__ __forceinline__ void wgmma_ss_n72(float (&d)[36], uint64_t da, uint64_t db, int scale_d) {
  asm volatile("{\n.reg .pred p;\nsetp.ne.b32 p, %38, 0;\n"
    "wgmma.mma_async.sync.aligned.m64n72k16.f32.bf16.bf16 {%0, %1, %2, %3, %4, %5, %6, %7, %8, %9, %10, %11, %12, %13, %14, %15, %16, %17, %18, %19, %20, %21, %22, %23, %24, %25, %26, %27, %28, %29, %30, %31, %32, %33, %34, %35}, %36, %37, p, %41, 1, %39, %40;\n}\n"
    : "+f"(d[0]), "+f"(d[1]), "+f"(d[2]), "+f"(d[3]), "+f"(d[4]), "+f"(d[5]), "+f"(d[6]), "+f"(d[7]), "+f"(d[8]), "+f"(d[9]), "+f"(d[10]), "+f"(d[11]), "+f"(d[12]), "+f"(d[13]), "+f"(d[14]), "+f"(d[15]), "+f"(d[16]), "+f"(d[17]), "+f"(d[18]), "+f"(d[19]), "+f"(d[20]), "+f"(d[21]), "+f"(d[22]), "+f"(d[23]), "+f"(d[24]), "+f"(d[25]), "+f"(d[26]), "+f"(d[27]), "+f"(d[28]), "+f"(d[29]), "+f"(d[30]), "+f"(d[31]), "+f"(d[32]), "+f"(d[33]), "+f"(d[34]), "+f"(d[35])
    : "l"(da), "l"(db), "r"(scale_d), "n"(TA), "n"(TB), "n"(SA));
}
template<int TB, int SA=1> __device__ __forceinline__ void wgmma_rs_n40(float (&d)[20], uint32_t a0, uint32_t a1, uint32_t a2, uint32_t a3, uint64_t db, int scale_d) {
  asm volatile("{\n.reg .pred p;\nsetp.ne.b32 p, %25, 0;\n"
    "wgmma.mma_async.sync.aligned.m64n40k16.f32.bf16.bf16 {%0, %1, %2, %3, %4, %5, %6, %7, %8, %9, %10, %11, %12, %13, %14, %15, %16, %17, %18, %19}, {%20, %21, %22, %23}, %24, p, %27, 1, %26;\n}\n"
    : "+f"(d[0]), "+f"(d[1]), "+f"(d[2]), "+f"(d[3]), "+f"(d[4]), "+f"(d[5]), "+f"(d[6]), "+f"(d[7]), "+f"(d[8]), "+f"(d[9]), "+f"(d[10]), "+f"(d[11]), "+f"(d[12]), "+f"(d[13]), "+f"(d[14]), "+f"(d[15]), "+f"(d[16]), "+f"(d[17]), "+f"(d[18]), "+f"(d[19])
    : "r"(a0), "r"(a1), "r"(a2), "r"(a3), "l"(db), "r"(scale_d), "n"(TB), "n"(SA));
}
template<int TB> __device__ __forceinline__ void wgmma_hrs_n64(uint32_t (&d)[16], uint32_t a0, uint32_t a1, uint32_t a2, uint32_t a3, uint64_t db, int scale_d) {
  asm volatile("{\n.reg .pred p;\nsetp.ne.b32 p, %21, 0;\n"
    "wgmma.mma_async.sync.aligned.m64n64k16.f16.f16.f16 {%0, %1, %2, %3, %4, %5, %6, %7, %8, %9, %10, %11, %12, %13, %14, %15}, {%16, %17, %18, %19}, %20, p, 1, 1, %22;\n}\n"
    : "+r"(d[0]), "+r"(d[1]), "+r"(d[2]), "+r"(d[3]), "+r"(d[4]), "+r"(d[5]), "+r"(d[6]), "+r"(d[7]), "+r"(d[8]), "+r"(d[9]), "+r"(d[10]), "+r"(d[11]), "+r"(d[12]), "+r"(d[13]), "+r"(d[14]), "+r"(d[15])
    : "r"(a0), "r"(a1), "r"(a2), "r"(a3), "l"(db), "r"(scale_d), "n"(TB));
}
template<int TB> __device__ __forceinline__ void wgmma_hrs_n32(uint32_t (&d)[8], uint32_t a0, uint32_t a1, uint32_t a2, uint32_t a3, uint64_t db, int scale_d) {
  asm volatile("{\n.reg .pred p;\nsetp.ne.b32 p, %13, 0;\n"
    "wgmma.mma_async.sync.aligned.m64n32k16.f16.f16.f16 {%0, %1, %2, %3, %4, %5, %6, %7}, {%8, %9, %10, %11}, %12, p, 1, 1, %14;\n}\n"
    : "+r"(d[0]), "+r"(d[1]), "+r"(d[2]), "+r"(d[3]), "+r"(d[4]), "+r"(d[5]), "+r"(d[6]), "+r"(d[7])
    : "r"(a0), "r"(a1), "r"(a2), "r"(a3), "l"(db), "r"(scale_d), "n"(TB));
}

__device__ __align__(128) const uint32_t c_thr[1536] = {
  0x33fb33ff,0xa49c9de4,0x33273352,0xaf2cae76,0x33e233f1,0xa96ca7bd,0x32c432f7,0xb045afdd,0x33b733cf,0xac3eaaf7,0x3250328c,0xb0eab099,
  0x3378339a,0xadbcacff,0x31cd3211,0xb182b137,0x33d033fb,0xaadea46a,0x299e2d17,0xb3e0b396,0x32fb337a,0xafd2adb1,0xa78b1f76,0xb3f2b3ff,
  0x318b3254,0xb1c5b0e5,0xae6bac32,0xb354b3b8,0x2f4230a3,0xb321b285,0xb133b040,0xb215b2c7,0x337c33f2,0xada5a759,0xb179afc8,0xb1d6b2fe,
  0x31463293,0xb204b08e,0xb394b2ba,0xad23b055,0x2b402f4e,0xb3cbb31e,0xb3e4b3f9,0x293ba533,0xac269c52,0xb3bab400,0xb258b357,0x30e02e5f,
  0x330133e5,0xafbda922,0xb3f3b3c9,0x2727ab59,0x2deb314a,0xb36fb200,0xb194b32f,0x31bc2f0a,0xacdb2084,0xb39fb3ff,0xa565aea4,0x33f93347,
  0xb2b6b0db,0xb05ab25c,0x30892c1a,0x329733bc,0x326033d4,0xb0d6aa94,0xb00ab29b,0x32e83084,0x20e82f64,0xb3feb318,0x2d8da597,0x338133f8,
  0xb1fcae48,0xb14fb35c,0x339031b8,0x2d3a3199,0xb3e6b3ae,0x2909ac7b,0x32d133f4,0xb030a6f5,0x319d33bf,0xb1b3ac02,0x2e3ca874,0x335e33ec,
  0xacc32b89,0xb3a3b3c6,0x33f83276,0x25c930b7,0xb3dcb1f8,0xaa01b154,0x30653335,0xb2b0aef4,0xb107b383,0x32392d81,0xafa6214d,0xb307b3fe,
  0x30bc33a5,0xb273acb7,0x33c5311b,0x2ba23229,0xb0cc94b6,0xb267b400,0x30153360,0xb2e1ae31,0xb385b3ab,0x2d76ac93,0xb166a691,0xb1e7b3f5,
  0x22deb06a,0x33fd32ac,0xb337b3da,0x2ee8aa19,0x2f853387,0xb310ad6a,0x322d33fe,0xb1162216,0xb2a9abd3,0xb06fb3c2,0xb07428a6,0xb2a5b3ea,
  0xb111b3e9,0x323128be,0xb30db3c3,0x2f90abba,0x31aa227a,0x31a633fd,0x2e25ad5e,0x33633389,0x2d6a3365,0xb387ae1a,0xa21631aa,0xb3feb1a6,
  0xb3c2af85,0xabd3b310,0xb3eab22d,0x28a6b116,0xa8beb2a9,0x33e9306f,0x2bbab074,0x33c332a5,0x33fd3111,0x227a3231,0x3389330d,0xad5e2f90,
  0x2a63333f,0xb3d7aec6,0xb2a2a1b1,0xb07ab3fe,0xb3f7b158,0x25fbb1f4,0xacb7b38b,0x33a52d52,0x2e0eb025,0x336832d8,0x340030bc,0x14b63273,
  0x323533c0,0xb10c2beb,0xac9330cc,0xb3abb267,0x23433316,0xb3fdaf6f,0xb38eb225,0x2d46b11f,0xb342b29e,0x2ebbb07f,0x31e3aa7c,0x316b33d6,
  0x3264a6c3,0x30d133f5,0x2c0233ac,0xb3bfac87,0x28f0336a,0xb3e7ae02,0xb3c6b19d,0x2b89b1b3,0xa59732e8,0xb3f8b00a,0xaccfb3ed,0x33a1285b,
  0xb1b8b381,0x3199ad8d,0x336c31df,0xadf73170,0x33f42d3a,0x26f53390,0xb30423a7,0xafb2b3fc,0xb05f3030,0xb2b3b2d1,0x29e8b27a,0x33dd30b2,
  0xab5932b6,0xb3c9b05a,0x30adb089,0x327e3297,0xaf0ab3f3,0x332fa727,0x240633b0,0xb3fcac6f,0x33473194,0xaea431bc,0xb174b359,0x31daae54,
  0xb3bca565,0xac1ab3f9,0x33ee2f59,0xa842331b,0xaddf3281,0xb371b0a8,0x34002b40,0x1c5233cb,0xa759b3ef,0x33f22829,0xb2fe2c26,0xafc8b3ba,
  0x308e337c,0xb2932da5,0x3055b179,0x32ba31d6,0xb31eb146,0x2f4eb204,0xa5333394,0xb3f9ad23,0xaff33249,0xb2f1b0f3,0x30e532fb,0xb2542fd2,
  0x2b28b373,0x33cc2dd4,0xb285b18b,0x30a3b1c5,0x246a33fa,0xb3fba500,0x33962f42,0xad173321,0xadb1b3d0,0x337aaade,0xb3ffa99e,0x1f76b3e0,
  0xb0ee320d,0xb24db13c,0xac4b3398,0xb3b5ad0b,0x304ab289,0x32c1309e,0x2985b3ce,0x33e12b0f,0xaf3732f4,0xb324afe8,0xa4ce33f0,0xb3faa7ef,
  0x2dc8b34f,0x33762e82,0x9de4b3ff,0x33ff1ead,0xb1c931cd,0xb186b182,0xb3762e82,0xadc8b34f,0x324db13c,0x30ee320d,0x33b5ad0b,0x2c4b3398,
  0xb2c1309e,0xb04ab289,0xb3e12b0f,0xa985b3ce,0x3324afe8,0x2f3732f4,0x33faa7ef,0x24ce33f0,0xb285318b,0xb0a3b1c5,0xb2c7ae6b,0x3040b354,
  0x3396af42,0x2d173321,0x31413133,0xb2093215,0xb3ff299e,0x9f76b3e0,0xae8db2bd,0x334cb050,0x33b8278b,0xac3233f2,0x281033b3,0xb3ef2c57,
  0xb31e3146,0xaf4eb204,0xa533b394,0x33f9ad23,0x3400ab40,0x9c5233cb,0xae5f33e4,0xb357a93b,0xb2feac26,0x2fc8b3ba,0x3245b258,0x30f830e0,
  0x30553179,0xb2ba31d6,0xb3df2e99,0xa9b6b34a,0xb39230fd,0xad2fb241,0x3200b301,0x314a2fbd,0x337f1b11,0xad993400,0xb3ff2deb,0xa084b36f,
  0xb005b129,0x32ebb21d,0x325c2cdb,0xb0db339f,0xa92233de,0xb3e529cf,0xab59b2b6,0x33c9b05a,0xb3dd30b2,0xa9e8b27a,0x33d4ab71,0xaa9433c8,
  0x32212c0e,0xb12433bd,0xaf64b0d6,0x3318b260,0x197fb345,0x3400aeaf,0xae4833fe,0xb35c20e8,0xb23d3332,0xb102aeff,0x33aeb14f,0x2c7b31fc,
  0xb3fe3065,0xa14db2b0,0x2ebb307f,0xb342329e,0x300f2fa6,0xb2e53307,0x30d1b3f5,0x326426c3,0x302ab400,0x32d517db,0xb3e72e02,0x28f0b36a,
  0xb3fd2f6f,0x2343b316,0x2d46311f,0xb38e3225,0xb3f53015,0x2691b2e1,0xaf9b33eb,0xb30a288d,0x2a193166,0xb3da31e7,0x33d7aec6,0xaa63333f,
  0x3313b337,0x2f7a2ee8,0xa5fbb1f4,0x33f7b158,0xb1a1a8d7,0x31afb3e8,0xb36832d8,0xae0eb025,0xb3c22f85,0x2bd3b310,0xb3ea322d,0xa8a6b116,
  0xa8be32a9,0xb3e9306f,0x2bba3074,0xb3c332a5,0x33fdb111,0xa27a3231,0x3389b30d,0x2d5e2f90,0xa216b1aa,0x33feb1a6,0xaed2ae25,0x333db363,
  0xb3652edd,0x2e1ab33a,0xb1aa227a,0x31a6b3fd,0xaf853387,0xb3102d6a,0xb22d33fe,0xb116a216,0x32a9abd3,0xb06f33c2,0x307428a6,0xb2a533ea,
  0x3111b3e9,0x3231a8be,0x330db3c3,0x2f902bba,0xb2e12e31,0x3015b360,0x288db1a1,0x33ebb1af,0xb1e733f5,0xb1662691,0xb33f2f9b,0x2ec6b30a,
  0x2ee82a19,0xb33733da,0xb15833d7,0xb1f42a63,0x33e8b313,0x28d72f7a,0x302525fb,0xb2d833f7,0xb2392d81,0x3107b383,0x3307b3fe,0x2fa6214d,
  0xb35e33ec,0xae3ca874,0x97dbb00f,0x3400b2e5,0xa5c930b7,0xb3f83276,0xb316302a,0x2f6fb2d5,0x32b0aef4,0xb0653335,0xb29e33fd,0xb07f2343,
  0xb1702ccf,0x31dfb3a1,0x3345b124,0xaeaf3221,0xb3fc336c,0xa3a7adf7,0x3332b400,0x2eff997f,0xb0b23304,0xb27a2fb2,0x2b71b102,0x33c8b23d,
  0x2c0e29e8,0xb3bd33dd,0xb0d62a94,0x3260b3d4,0xb0892c1a,0x3297b3bc,0x2aad2842,0xb3d333ee,0xb3b0327e,0x2c6fb0ad,0x3241b035,0xb0fd32ce,
  0xb35933fc,0xae542406,0x3400b392,0x1b112d2f,0xaf5931da,0xb31b3174,0x321db37f,0x3129ad99,0xaf152ac6,0x332cb3d2,0xb1463293,0xb204308e,
  0xb281312e,0x30a8b219,0xab402f4e,0xb3cb331e,0xb3ef3371,0x2829addf,0x2c269c52,0xb3ba3400,0xb37c33f2,0xada52759,0x3179afc8,0xb1d632fe,
  0xacf32953,0x339cb3e3,0xb3fa33cc,0x2500ab28,0xb0942f21,0x3290b32a,0xb3d033fb,0xaade246a,0xb249317d,0x30f3b1d2,0xb2fb337a,0xafd22db1,
  0xb37332f1,0x2dd4aff3,0xb18b3254,0xb1c530e5,0xa96c27bd,0x33e2b3f1,0xb0452fdd,0x32c4b2f7,0xac3e2af7,0x33b7b3cf,0xb0ea3099,0x3250b28c,
  0xadbc2cff,0x3378b39a,0xb1823137,0x31cdb211,0xaf2c2e76,0x3327b352,0xb20d31c9,0x313cb186,0x313c3186,0xb20db1c9,0x2d0b2dc8,0xb398b376,
  0x309e30ee,0xb289b24d,0x2b0f2c4b,0xb3ceb3b5,0x2fe8304a,0xb2f4b2c1,0x27ef2985,0xb3f0b3e1,0x2e822f37,0xb34fb324,0x1ead24ce,0xb3ffb3fa,
  0xb2bdb209,0xb050b141,0xb290b32a,0x30942f21,0xb3b3b34c,0xac57ae8d,0xb0f3b1d2,0x3249317d,0xb400b3ef,0x1d1ba810,0xadd4aff3,0x337332f1,
  0xb39cb3e3,0x2cf32953,0xa500ab28,0x33fa33cc,0xae99b0f8,0x334a3245,0x33ff33b2,0x201f2c63,0x2438a9b6,0x33fc33df,0x332c33d2,0xaf15aac6,
  0x303a2ce7,0x32cb339e,0x30a83219,0xb281b12e,0x32ee31c0,0x2ffe3190,0x28292ddf,0xb3efb371,0x33b0327e,0x2c6f30ad,0xb241b035,0xb0fdb2ce,
  0x335933fc,0xae54a406,0xb400b392,0x1b11ad2f,0x2f5931da,0xb31bb174,0xb21db37f,0x31292d99,0xaaad2842,0xb3d3b3ee,0xa9cfb005,0x33de32eb,
  0x285b305f,0xb3edb2b3,0x2c0ea9e8,0x33bd33dd,0xb170accf,0xb1dfb3a1,0x33453124,0x2eaf3221,0xb3fcb36c,0x23a7adf7,0x33323400,0xaeff997f,
  0xb0b2b304,0x327a2fb2,0x2b713102,0xb3c8b23d,0xb400b2e5,0x17dbb00f,0x2e023264,0xb36ab0d1,0xaf6fb2d5,0x3316302a,0xb11fa8f0,0xb225b3e7,
  0x307f2343,0x329e33fd,0xb3d6b38e,0x2a7cad46,0x33f53342,0xa6c32ebb,0xac87b1e3,0x33ac316b,0x28d7af7a,0x33e83313,0xb2d8b3f7,0x3025a5fb,
  0x33eb31af,0x288d31a1,0x2bebae0e,0x33c03368,0x2ec6330a,0xb33faf9b,0x33fe3235,0x21b1310c,0xb1f4aa63,0xb158b3d7,0x2d5232a2,0xb38bb07a,
  0x33a7333d,0xacab2ed2,0x33f63162,0x262d31eb,0xaa4b301a,0xb3d8b2de,0x2a32326b,0xb3d9b0c7,0xb3f6b26f,0x265fb0c1,0xb3a9b020,0xac9fb2db,
  0x0e48b15d,0x340031f0,0xae1ab33a,0x33652edd,0xaed22e25,0xb33db363,0xb1eb0e48,0xb162b400,0xb2deb3a7,0x301aacab,0xb0c7b3f6,0x326b262d,
  0x30c1aa4b,0x326f33d8,0x32db2a32,0x302033d9,0x31f033f6,0xb15d265f,0x2edd33a9,0xb33aac9f,0xb2acb385,0x306aad76,0x2a19b166,0x33da31e7,
  0x3229a2de,0x311b33fd,0x33133337,0xaf7a2ee8,0x2e3133c5,0xb360aba2,0xb1a128d7,0xb1afb3e8,0xb3f5b015,0xa691b2e1,0xaf9bb3eb,0x330a288d,
  0x3154acc3,0x31f833a3,0x2ef433f8,0xb335a5c9,0x2d8133dc,0xb383aa01,0xb3feb065,0x214db2b0,0xb3ecb107,0x2874b239,0x300fafa6,0x32e53307,
  0x30b7ae3c,0x3276335e,0x302a3400,0xb2d517db,0x312433bd,0xb2212c0e,0xb318b260,0x2f64b0d6,0xb400aeaf,0x997fb345,0x335c20e8,0x2e4833fe,
  0x3102aeff,0x323d3332,0xac7b31fc,0xb3aeb14f,0x2a9433c8,0xb3d4ab71,0xb084b3e6,0x329ba909,0xb2ce2aad,0xb035b3d3,0x33e529cf,0x292233de,
  0x2d2fb241,0x339230fd,0xb14a2fbd,0xb200b301,0x2d993400,0xb37f1b11,0x2084b36f,0x33ff2deb,0xb2ebb21d,0x3005b129,0x30db339f,0xb25c2cdb,
  0xae5fb3e4,0x3357a93b,0xb190303a,0xb1c0b2cb,0x32453258,0xb0f830e0,0x2c63b2ee,0x33b22ffe,0xb3dfae99,0x29b6b34a,0x2ac633ff,0xb3d2a01f,
  0x339ea438,0x2ce733fc,0xb12eb32c,0x3219af15,0x33b8a78b,0x2c3233f2,0x2810b3b3,0x33ef2c57,0xb2c72e6b,0xb040b354,0x29533400,0xb3e31d1b,
  0x3141b133,0x32093215,0xaf21b39c,0x332aacf3,0xae8d32bd,0xb34cb050,0x317d3290,0xb1d23094,0x27bd33fb,0xb3f1249c,0x2fdd3327,0xb2f72f2c,
  0xaaf7b3e2,0x33cfa96c,0xb099b2c4,0x328cb045,0x2cff33b7,0xb39a2c3e,0x31373250,0xb21130ea,0xae76b378,0x3352adbc,0xb1c9b1cd,0x3186b182,
  0xb3ff1ead,0x1de4b3ff,0xb352adbc,0x2e76b378,0x33f1249c,0xa7bd33fb,0x32f72f2c,0xafdd3327,0xb3cfa96c,0x2af7b3e2,0xb28cb045,0x3099b2c4,
  0x339a2c3e,0xacff33b7,0x321130ea,0xb1373250,0x2953b400,0x33e31d1b,0x33ccadd4,0x2b283373,0xaf21339c,0xb32aacf3,0xb3fb2500,0x246ab3fa,
  0x317db290,0x31d23094,0x337a2ade,0xadb133d0,0xb2f130f3,0xaff3b249,0xb254afd2,0x30e5b2fb,0x339e2438,0xace733fc,0xb12e332c,0xb219af15,
  0xb190b03a,0x31c0b2cb,0x3371b0a8,0x2ddf3281,0x2c6332ee,0xb3b22ffe,0xb3f22829,0x2759b3ef,0x2ac6b3ff,0x33d2a01f,0x32932da5,0xb08e337c,
  0xaf0a33f3,0xb32fa727,0x2406b3b0,0x33fcac6f,0x3347b194,0x2ea431bc,0xb1743359,0xb1daae54,0xb3bc2565,0x2c1ab3f9,0x33eeaf59,0x2842331b,
  0x30ad3089,0xb27e3297,0xb2ceaaad,0x3035b3d3,0xb29ba909,0x3084b3e6,0x305f3030,0xb2b332d1,0x259732e8,0xb3f8300a,0x2ccfb3ed,0x33a1a85b,
  0x31b8b381,0x31992d8d,0xb36c31df,0xadf7b170,0xb3f42d3a,0x26f5b390,0x330423a7,0xafb233fc,0x316bb3d6,0x31e32a7c,0xb3832a01,0x2d81b3dc,
  0xb3bf2c87,0x2c02b3ac,0x28743239,0xb3ec3107,0x2b8931b3,0xb3c6319d,0x3276b35e,0x30b72e3c,0x31f8b3a3,0x31542cc3,0xb33525c9,0x2ef4b3f8,
  0x310c2beb,0xb23533c0,0x33abb267,0x2c9330cc,0x307ab3fe,0x32a2a1b1,0xb06aad76,0x32acb385,0xb3a52d52,0x2cb7b38b,0xb11b33fd,0xb229a2de,
  0x94b63273,0xb40030bc,0x3360aba2,0xae3133c5,0xb2de33a7,0xb01aacab,0xb0c733f6,0xb26b262d,0x30c12a4b,0xb26f33d8,0x32dbaa32,0xb02033d9,
  0x31f0b3f6,0x315d265f,0x2eddb3a9,0x333aac9f,0xb1eb8e48,0x3162b400,0xb3872e1a,0x2d6ab365,0xae25ad5e,0x3363b389,0x8e48b15d,0x3400b1f0,
  0xb3a7333d,0xacabaed2,0xb3f63162,0x262db1eb,0x2a4b301a,0xb3d832de,0xaa32326b,0xb3d930c7,0x33f6b26f,0x265f30c1,0x33a9b020,0xac9f32db,
  0x33c0b368,0x2beb2e0e,0x30cc94b6,0xb2673400,0x21b1b10c,0x33feb235,0x3385b3ab,0x2d762c93,0xb38b307a,0x2d52b2a2,0xa2deb06a,0x33fdb2ac,
  0xb0bc33a5,0xb2732cb7,0xb3c5311b,0x2ba2b229,0x26c32ebb,0xb3f53342,0xb3ac316b,0x2c87b1e3,0x336ab0d1,0xae023264,0xb19d33bf,0xb1b32c02,
  0x3225b3e7,0x311fa8f0,0x2cc32b89,0xb3a333c6,0xaa7cad46,0x33d6b38e,0x33dcb1f8,0xaa013154,0xb3fe3318,0x20e8af64,0x3381b3f8,0x2d8d2597,
  0xb14f335c,0xb1fc2e48,0x2d3ab199,0x3390b1b8,0x29092c7b,0xb3e633ae,0xb03026f5,0x32d1b3f4,0x32e8b084,0xb00a329b,0xb3ed32b3,0x285bb05f,
  0x29cfb005,0x33deb2eb,0xb05a325c,0xb2b630db,0xafbd2922,0x3301b3e5,0x27272b59,0xb3f333c9,0xb36f3200,0x2debb14a,0x31bcaf0a,0xb194332f,
  0xb39f33ff,0xacdba084,0x33f9b347,0xa5652ea4,0x3394b2ba,0xad233055,0xa438a9b6,0x33fcb3df,0x33e4b3f9,0x293b2533,0xb03a2ce7,0x32cbb39e,
  0x3258b357,0x30e0ae5f,0xb2ee31c0,0x2ffeb190,0x2e99b0f8,0x334ab245,0xb3ff33b2,0x201fac63,0xaf4230a3,0xb3213285,0x3133b040,0xb21532c7,
  0xa99e2d17,0xb3e03396,0x32bdb209,0xb0503141,0x278b1f76,0xb3f233ff,0x33b3b34c,0xac572e8d,0x2e6bac32,0xb35433b8,0x3400b3ef,0x1d1b2810,
  0xb289324d,0x309eb0ee,0xb3ce33b5,0x2b0fac4b,0xb2f432c1,0x2fe8b04a,0xb3f033e1,0x27efa985,0xb34f3324,0x2e82af37,0xb3ff33fa,0x1eada4ce,
  0xb3983376,0x2d0badc8,0xb3fb33ff,0xa49c1de4,0x351c35f6,0xac93a617,0xb8a3b93c,0x308d2a16,0x32f43448,0xb160afa5,0xb6a4b7fe,0x353a3389,
  0x2fa53160,0xb448b2f4,0xb389b53a,0x37fe36a4,0x26172c93,0xb5f6b51c,0xaa16b08d,0x393c38a3,0x34c3358c,0xac47a5b2,0xb85fb8f3,0x304229b1,
  0x327e33fd,0xb106af26,0xb63cb785,0x34e7330f,0x2f263106,0xb3fdb27e,0xb30fb4e7,0x3785363c,0x25b22c47,0xb58cb4c3,0xa9b1b042,0x38f3385f,
  0x346a3523,0xabf6a54d,0xb81ab8a8,0x2fef294d,0x3209336b,0xb0acaea7,0xb5d4b70a,0x34933294,0x2ea730ac,0xb36bb209,0xb294b493,0x370a35d4,
  0x254d2bf6,0xb523b46a,0xa94dafef,0x38a8381a,0x341334bc,0xab5fa4e9,0xb7a6b85a,0x2f5928e8,0x319432da,0xb052ae28,0xb56ab68d,0x343e3219,
  0x2e283052,0xb2dab194,0xb219b43e,0x368d356a,0x24e92b5f,0xb4bcb413,0xa8e8af59,0x385a37a6,0x33783456,0xaac8a484,0xb715b80a,0x2ec32884,
  0x3120324a,0xaff2ada9,0xb4ffb60e,0x33d3319e,0x2da92ff2,0xb24ab120,0xb19eb3d3,0x360e34ff,0x24842ac8,0xb456b378,0xa884aec3,0x380a3715,
  0x32cd33e3,0xaa31a420,0xb682b76f,0x2e2d281f,0x30ac31bb,0xaf3fad2a,0xb493b58d,0x33283122,0x2d2a2f3f,0xb1bbb0ac,0xb122b328,0x358d3493,
  0x24202a31,0xb3e3b2cd,0xa81fae2d,0x376f3682,0x3223331c,0xa999a376,0xb5ebb6c6,0x2d972776,0x3039312d,0xae8dacac,0xb426b50b,0x327c30a6,
  0x2cac2e8d,0xb12db039,0xb0a6b27c,0x350b3426,0x23762999,0xb31cb223,0xa776ad97,0x36c635eb,0x317a3257,0xa902a2ad,0xb552b61a,0x2d0026ad,
  0x2f8c309f,0xaddcac2e,0xb371b487,0x31cf3029,0x2c2e2ddc,0xb09faf8c,0xb029b1cf,0x34873371,0x22ad2902,0xb257b17a,0xa6adad00,0x361a3552,
  0x30d23194,0xa86ba1e4,0xb4b7b56a,0x2c6a25e4,0x2ea73012,0xad2aab5f,0xb294b402,0x31222f59,0x2b5f2d2a,0xb012aea7,0xaf59b122,0x34023294,
  0x21e4286b,0xb194b0d2,0xa5e4ac6a,0x356a34b7,0x302c30d2,0xa7a9a11b,0xb41ab4b7,0x2ba7251b,0x2dc22f0c,0xac79aa63,0xb1b6b2f7,0x30742e5f,
  0x2a632c79,0xaf0cadc2,0xae5fb074,0x32f731b6,0x211b27a9,0xb0d2b02c,0xa51baba7,0x34b7341a,0x2f0c3012,0xa67ba052,0xb2f7b402,0x2a7a2452,
  0x2cde2df5,0xab91a967,0xb0d7b1e8,0x2f8b2d65,0x29672b91,0xadf5acde,0xad65af8b,0x31e830d7,0x2052267b,0xb012af0c,0xa452aa7a,0x340232f7,
  0x2dc22ea7,0xa54d9f12,0xb1b6b294,0x294d2311,0x2bf62cde,0xaa31a86b,0xafefb0d7,0x2e2d2c6a,0x286b2a31,0xacdeabf6,0xac6aae2d,0x30d72fef,
  0x1f12254d,0xaea7adc2,0xa311a94d,0x329431b6,0x2c792d2a,0xa4209d7f,0xb074b122,0x281f217f,0x2a312b91,0xa8d0a6e0,0xae2daf8b,0x2cce2ade,
  0x26e028d0,0xab91aa31,0xaadeacce,0x2f8b2e2d,0x1d7f2420,0xad2aac79,0xa17fa81f,0x31223074,0x2a632b5f,0xa1e49bdb,0xae5faf59,0x25e41fdb,
  0x286b2967,0xa6e0a4e9,0xac6aad65,0x2ade28e8,0x24e926e0,0xa967a86b,0xa8e8aade,0x2d652c6a,0x1bdb21e4,0xab5faa63,0x9fdba5e4,0x2f592e5f,
  0x27a9286b,0x9f1298b6,0xaba7ac6a,0x23111cb6,0x254d267b,0xa420a1e4,0xa94daa7a,0x281f25e4,0x21e42420,0xa67ba54d,0xa5e4a81f,0x2a7a294d,
  0x18b61f12,0xa86ba7a9,0x9cb6a311,0x2c6a2ba7,0x211b21e4,0x98b69248,0xa51ba5e4,0x1cb61648,0x1f122052,0x9d7f9bdb,0xa311a452,0x217f1fdb,
  0x1bdb1d7f,0xa0529f12,0x9fdba17f,0x24522311,0x124818b6,0xa1e4a11b,0x96489cb6,0x25e4251b,0xa11ba1e4,0x18b61248,0x251b25e4,0x9cb69648,
  0x9f12a052,0x1d7f1bdb,0x23112452,0xa17f9fdb,0x9bdb9d7f,0x20521f12,0x1fdb217f,0xa452a311,0x924898b6,0x21e4211b,0x16481cb6,0xa5e4a51b,
  0xa7a9a86b,0x1f1218b6,0x2ba72c6a,0xa3119cb6,0xa54da67b,0x242021e4,0x294d2a7a,0xa81fa5e4,0xa1e4a420,0x267b254d,0x25e4281f,0xaa7aa94d,
  0x98b69f12,0x286b27a9,0x1cb62311,0xac6aaba7,0xaa63ab5f,0x21e41bdb,0x2e5f2f59,0xa5e49fdb,0xa86ba967,0x26e024e9,0x2c6a2d65,0xaadea8e8,
  0xa4e9a6e0,0x2967286b,0x28e82ade,0xad65ac6a,0x9bdba1e4,0x2b5f2a63,0x1fdb25e4,0xaf59ae5f,0xac79ad2a,0x24201d7f,0x30743122,0xa81fa17f,
  0xaa31ab91,0x28d026e0,0x2e2d2f8b,0xacceaade,0xa6e0a8d0,0x2b912a31,0x2ade2cce,0xaf8bae2d,0x9d7fa420,0x2d2a2c79,0x217f281f,0xb122b074,
  0xadc2aea7,0x254d1f12,0x31b63294,0xa94da311,0xabf6acde,0x2a31286b,0x2fef30d7,0xae2dac6a,0xa86baa31,0x2cde2bf6,0x2c6a2e2d,0xb0d7afef,
  0x9f12a54d,0x2ea72dc2,0x2311294d,0xb294b1b6,0xaf0cb012,0x267b2052,0x32f73402,0xaa7aa452,0xacdeadf5,0x2b912967,0x30d731e8,0xaf8bad65,
  0xa967ab91,0x2df52cde,0x2d652f8b,0xb1e8b0d7,0xa052a67b,0x30122f0c,0x24522a7a,0xb402b2f7,0xb02cb0d2,0x27a9211b,0x341a34b7,0xaba7a51b,
  0xadc2af0c,0x2c792a63,0x31b632f7,0xb074ae5f,0xaa63ac79,0x2f0c2dc2,0x2e5f3074,0xb2f7b1b6,0xa11ba7a9,0x30d2302c,0x251b2ba7,0xb4b7b41a,
  0xb0d2b194,0x286b21e4,0x34b7356a,0xac6aa5e4,0xaea7b012,0x2d2a2b5f,0x32943402,0xb122af59,0xab5fad2a,0x30122ea7,0x2f593122,0xb402b294,
  0xa1e4a86b,0x319430d2,0x25e42c6a,0xb56ab4b7,0xb17ab257,0x290222ad,0x3552361a,0xad00a6ad,0xaf8cb09f,0x2ddc2c2e,0x33713487,0xb1cfb029,
  0xac2eaddc,0x309f2f8c,0x302931cf,0xb487b371,0xa2ada902,0x3257317a,0x26ad2d00,0xb61ab552,0xb223b31c,0x29992376,0x35eb36c6,0xad97a776,
  0xb039b12d,0x2e8d2cac,0x3426350b,0xb27cb0a6,0xacacae8d,0x312d3039,0x30a6327c,0xb50bb426,0xa376a999,0x331c3223,0x27762d97,0xb6c6b5eb,
  0xb2cdb3e3,0x2a312420,0x3682376f,0xae2da81f,0xb0acb1bb,0x2f3f2d2a,0x3493358d,0xb328b122,0xad2aaf3f,0x31bb30ac,0x31223328,0xb58db493,
  0xa420aa31,0x33e332cd,0x281f2e2d,0xb76fb682,0xb378b456,0x2ac82484,0x3715380a,0xaec3a884,0xb120b24a,0x2ff22da9,0x34ff360e,0xb3d3b19e,
  0xada9aff2,0x324a3120,0x319e33d3,0xb60eb4ff,0xa484aac8,0x34563378,0x28842ec3,0xb80ab715,0xb413b4bc,0x2b5f24e9,0x37a6385a,0xaf59a8e8,
  0xb194b2da,0x30522e28,0x356a368d,0xb43eb219,0xae28b052,0x32da3194,0x3219343e,0xb68db56a,0xa4e9ab5f,0x34bc3413,0x28e82f59,0xb85ab7a6,
  0xb46ab523,0x2bf6254d,0x381a38a8,0xafefa94d,0xb209b36b,0x30ac2ea7,0x35d4370a,0xb493b294,0xaea7b0ac,0x336b3209,0x32943493,0xb70ab5d4,
  0xa54dabf6,0x3523346a,0x294d2fef,0xb8a8b81a,0xb4c3b58c,0x2c4725b2,0x385f38f3,0xb042a9b1,0xb27eb3fd,0x31062f26,0x363c3785,0xb4e7b30f,
  0xaf26b106,0x33fd327e,0x330f34e7,0xb785b63c,0xa5b2ac47,0x358c34c3,0x29b13042,0xb8f3b85f,0xb51cb5f6,0x2c932617,0x38a3393c,0xb08daa16,
  0xb2f4b448,0x31602fa5,0x36a437fe,0xb53ab389,0xafa5b160,0x344832f4,0x3389353a,0xb7feb6a4,0xa617ac93,0x35f6351c,0x2a16308d,0xb93cb8a3,
};
__device__ __align__(128) const uint32_t c_img[2560] = {
  0x326d31ed,0x333b32dd,0x33c33388,0x33fe33ea,0x33c331ed,0x31ed33c3,0xa8b22d64,0xb33bb0c4,0x33ea31ed,0xad64301d,0xb2ddb388,0x315fa8b2,
  0x32dd31ed,0xb3feabc6,0x326dad64,0xad64326d,0x30c431ed,0xaed7b2dd,0x2bc63388,0xa248b3ea,0x2bc631ed,0x315fb3c3,0xb3ea2d64,0x2ed730c4,
  0xa8b231ed,0x3388b01d,0x301db388,0xb1ed28b2,0xb01d31ed,0x22482bc6,0x30c4ad64,0x3388b26d,0x33ea33fe,0x338833c3,0x32dd333b,0x31ed326d,
  0xb2ddb3fe,0xa248b01d,0x326d2ed7,0x338833ea,0x30c433fe,0xb33babc6,0xabc6b33b,0x33fe30c4,0xabc6b3fe,0x31ed32dd,0xb3eaaed7,0x333ba8b2,
  0xa8b233fe,0x2d64b3c3,0xb01d333b,0x315fb26d,0x301db3fe,0xb3fe301d,0x30c42ed7,0x2d64b3ea,0xb26d33fe,0x2ed72bc6,0x33c3b33b,0xa248b0c4,
  0x33c3b3fe,0x315fb2dd,0x28b2aed7,0xaed728b2,0xb0c4b15f,0xaed7b01d,0xabc6ad64,0xa248a8b2,0xabc6b15f,0x315f2bc6,0x33ea3388,0x2ed7326d,
  0x28b2b15f,0x338832dd,0xb01d2d64,0xb1edb3ea,0x301db15f,0x224833c3,0xb0c4b388,0x338830c4,0x326db15f,0xb33b301d,0x33c3ad64,0xb3fe28b2,
  0x33c3b15f,0xb1edabc6,0xa8b23388,0x333bb26d,0x33eab15f,0x2d64b2dd,0xb2dd2d64,0xb15f33ea,0x32ddb15f,0x33feb3c3,0x326db388,0x2d64b0c4,
  0x28b22248,0x2d642bc6,0x301d2ed7,0x315f30c4,0xb01da248,0xb3feb2dd,0xb0c4b33b,0x2d64a8b2,0x326d2248,0x2ed733c3,0xb3c3aed7,0xa248b26d,
  0xb3c3a248,0x315fb01d,0xa8b2333b,0xaed7b3ea,0x33ea2248,0xb388abc6,0x32dd2ed7,0xb1edb0c4,0xb2dda248,0x224832dd,0x326db33b,0xb38828b2,
  0x30c42248,0x333bb3c3,0xabc6aed7,0xb3fe326d,0xabc6a248,0xb1ed301d,0xb3ea333b,0xb33b33ea,0xb26d31ed,0xb33b32dd,0xb3c33388,0xb3fe33ea,
  0xb3c331ed,0xb1ed33c3,0x28b22d64,0x333bb0c4,0xb3ea31ed,0x2d64301d,0x32ddb388,0xb15fa8b2,0xb2dd31ed,0x33feabc6,0xb26dad64,0x2d64326d,
  0xb0c431ed,0x2ed7b2dd,0xabc63388,0x2248b3ea,0xabc631ed,0xb15fb3c3,0x33ea2d64,0xaed730c4,0x28b231ed,0xb388b01d,0xb01db388,0x31ed28b2,
  0x301d31ed,0xa2482bc6,0xb0c4ad64,0xb388b26d,0xb3ea33fe,0xb38833c3,0xb2dd333b,0xb1ed326d,0x32ddb3fe,0x2248b01d,0xb26d2ed7,0xb38833ea,
  0xb0c433fe,0x333babc6,0x2bc6b33b,0xb3fe30c4,0x2bc6b3fe,0xb1ed32dd,0x33eaaed7,0xb33ba8b2,0x28b233fe,0xad64b3c3,0x301d333b,0xb15fb26d,
  0xb01db3fe,0x33fe301d,0xb0c42ed7,0xad64b3ea,0x326d33fe,0xaed72bc6,0xb3c3b33b,0x2248b0c4,0xb3c3b3fe,0xb15fb2dd,0xa8b2aed7,0x2ed728b2,
  0x30c4b15f,0x2ed7b01d,0x2bc6ad64,0x2248a8b2,0x2bc6b15f,0xb15f2bc6,0xb3ea3388,0xaed7326d,0xa8b2b15f,0xb38832dd,0x301d2d64,0x31edb3ea,
  0xb01db15f,0xa24833c3,0x30c4b388,0xb38830c4,0xb26db15f,0x333b301d,0xb3c3ad64,0x33fe28b2,0xb3c3b15f,0x31edabc6,0x28b23388,0xb33bb26d,
  0xb3eab15f,0xad64b2dd,0x32dd2d64,0x315f33ea,0xb2ddb15f,0xb3feb3c3,0xb26db388,0xad64b0c4,0xa8b22248,0xad642bc6,0xb01d2ed7,0xb15f30c4,
  0x301da248,0x33feb2dd,0x30c4b33b,0xad64a8b2,0xb26d2248,0xaed733c3,0x33c3aed7,0x2248b26d,0x33c3a248,0xb15fb01d,0x28b2333b,0x2ed7b3ea,
  0xb3ea2248,0x3388abc6,0xb2dd2ed7,0x31edb0c4,0x32dda248,0xa24832dd,0xb26db33b,0x338828b2,0xb0c42248,0xb33bb3c3,0x2bc6aed7,0x33fe326d,
  0x2bc6a248,0x31ed301d,0x33ea333b,0x333b33ea,0x30c4315f,0x2ed7301d,0x2bc62d64,0x224828b2,0x2bc6315f,0xb15fabc6,0xb3eab388,0xaed7b26d,
  0xa8b2315f,0xb388b2dd,0x301dad64,0x31ed33ea,0xb01d315f,0xa248b3c3,0x30c43388,0xb388b0c4,0xb26d315f,0x333bb01d,0xb3c32d64,0x33fea8b2,
  0xb3c3315f,0x31ed2bc6,0x28b2b388,0xb33b326d,0xb3ea315f,0xad6432dd,0x32ddad64,0x315fb3ea,0xb2dd315f,0xb3fe33c3,0xb26d3388,0xad6430c4,
  0xa8b2a248,0xad64abc6,0xb01daed7,0xb15fb0c4,0x301d2248,0x33fe32dd,0x30c4333b,0xad6428b2,0xb26da248,0xaed7b3c3,0x33c32ed7,0x2248326d,
  0x33c32248,0xb15f301d,0x28b2b33b,0x2ed733ea,0xb3eaa248,0x33882bc6,0xb2ddaed7,0x31ed30c4,0x32dd2248,0xa248b2dd,0xb26d333b,0x3388a8b2,
  0xb0c4a248,0xb33b33c3,0x2bc62ed7,0x33feb26d,0x2bc62248,0x31edb01d,0x33eab33b,0x333bb3ea,0x326d31ed,0x333b32dd,0x33c33388,0x33fe33ea,
  0x33c331ed,0x31ed33c3,0xa8b22d64,0xb33bb0c4,0x33ea31ed,0xad64301d,0xb2ddb388,0x315fa8b2,0x32dd31ed,0xb3feabc6,0x326dad64,0xad64326d,
  0x30c431ed,0xaed7b2dd,0x2bc63388,0xa248b3ea,0x2bc631ed,0x315fb3c3,0xb3ea2d64,0x2ed730c4,0xa8b231ed,0x3388b01d,0x301db388,0xb1ed28b2,
  0xb01d31ed,0x22482bc6,0x30c4ad64,0x3388b26d,0x33ea33fe,0x338833c3,0x32dd333b,0x31ed326d,0xb2ddb3fe,0xa248b01d,0x326d2ed7,0x338833ea,
  0x30c433fe,0xb33babc6,0xabc6b33b,0x33fe30c4,0xabc6b3fe,0x31ed32dd,0xb3eaaed7,0x333ba8b2,0xa8b233fe,0x2d64b3c3,0xb01d333b,0x315fb26d,
  0x301db3fe,0xb3fe301d,0x30c42ed7,0x2d64b3ea,0xb26d33fe,0x2ed72bc6,0x33c3b33b,0xa248b0c4,0x33c3b3fe,0x315fb2dd,0x28b2aed7,0xaed728b2,
  0xb0c4315f,0xaed7301d,0xabc62d64,0xa24828b2,0xabc6315f,0x315fabc6,0x33eab388,0x2ed7b26d,0x28b2315f,0x3388b2dd,0xb01dad64,0xb1ed33ea,
  0x301d315f,0x2248b3c3,0xb0c43388,0x3388b0c4,0x326d315f,0xb33bb01d,0x33c32d64,0xb3fea8b2,0x33c3315f,0xb1ed2bc6,0xa8b2b388,0x333b326d,
  0x33ea315f,0x2d6432dd,0xb2ddad64,0xb15fb3ea,0x32dd315f,0x33fe33c3,0x326d3388,0x2d6430c4,0x28b2a248,0x2d64abc6,0x301daed7,0x315fb0c4,
  0xb01d2248,0xb3fe32dd,0xb0c4333b,0x2d6428b2,0x326da248,0x2ed7b3c3,0xb3c32ed7,0xa248326d,0xb3c32248,0x315f301d,0xa8b2b33b,0xaed733ea,
  0x33eaa248,0xb3882bc6,0x32ddaed7,0xb1ed30c4,0xb2dd2248,0x2248b2dd,0x326d333b,0xb388a8b2,0x30c4a248,0x333b33c3,0xabc62ed7,0xb3feb26d,
  0xabc62248,0xb1edb01d,0xb3eab33b,0xb33bb3ea,0xb26d31ed,0xb33b32dd,0xb3c33388,0xb3fe33ea,0xb3c331ed,0xb1ed33c3,0x28b22d64,0x333bb0c4,
  0xb3ea31ed,0x2d64301d,0x32ddb388,0xb15fa8b2,0xb2dd31ed,0x33feabc6,0xb26dad64,0x2d64326d,0xb0c431ed,0x2ed7b2dd,0xabc63388,0x2248b3ea,
  0xabc631ed,0xb15fb3c3,0x33ea2d64,0xaed730c4,0x28b231ed,0xb388b01d,0xb01db388,0x31ed28b2,0x301d31ed,0xa2482bc6,0xb0c4ad64,0xb388b26d,
  0xb3ea33fe,0xb38833c3,0xb2dd333b,0xb1ed326d,0x32ddb3fe,0x2248b01d,0xb26d2ed7,0xb38833ea,0xb0c433fe,0x333babc6,0x2bc6b33b,0xb3fe30c4,
  0x2bc6b3fe,0xb1ed32dd,0x33eaaed7,0xb33ba8b2,0x28b233fe,0xad64b3c3,0x301d333b,0xb15fb26d,0xb01db3fe,0x33fe301d,0xb0c42ed7,0xad64b3ea,
  0x326d33fe,0xaed72bc6,0xb3c3b33b,0x2248b0c4,0xb3c3b3fe,0xb15fb2dd,0xa8b2aed7,0x2ed728b2,0x29ed29ed,0x29ed29ed,0x29ed29ed,0x29ed29ed,
  0x2bc32a6d,0x2add2bea,0x23c628c4,0xa81da0b2,0x2bc32add,0xa3c6281d,0xabc3aadd,0x23c6a81d,0x29ed2b3b,0xabfea564,0x295fa6d7,0x1a482b88,
  0x25642b88,0xa564ab88,0x25642b88,0xa564ab88,0xa0b22bc3,0x2a6daadd,0xabea23c6,0x28c4281d,0xa8c42bea,0x2a6da0b2,0x28c4abea,0xaa6d20b2,
  0xab3b2bfe,0xa564295f,0x26d79a48,0x2b88a9ed,0x29ed29ed,0x29ed29ed,0x29ed29ed,0x29ed29ed,0xabc3aa6d,0xaaddabea,0xa3c6a8c4,0x281d20b2,
  0x2bc32add,0xa3c6281d,0xabc3aadd,0x23c6a81d,0xa9edab3b,0x2bfe2564,0xa95f26d7,0x9a48ab88,0x25642b88,0xa564ab88,0x25642b88,0xa564ab88,
  0x20b2abc3,0xaa6d2add,0x2beaa3c6,0xa8c4a81d,0xa8c42bea,0x2a6da0b2,0x28c4abea,0xaa6d20b2,0x2b3babfe,0x2564a95f,0xa6d71a48,0xab8829ed,
  0x295f295f,0x295f295f,0x295f295f,0x295f295f,0x23c628c4,0xa81da0b2,0xabc3aa6d,0xaaddabea,0xa3c6281d,0xabc3aadd,0x23c6a81d,0x2bc32add,
  0xa95f26d7,0x9a48ab88,0x29ed2b3b,0xabfea564,0xab882564,0x2b88a564,0xab882564,0x2b88a564,0xabea23c6,0x28c4281d,0x20b2abc3,0xaa6d2add,
  0xaa6d20b2,0xa8c42bea,0x2a6da0b2,0x28c4abea,0xa6d71a48,0xab8829ed,0xab3b2bfe,0xa564295f,0x295f295f,0x295f295f,0x295f295f,0x295f295f,
  0xa3c6a8c4,0x281d20b2,0x2bc32a6d,0x2add2bea,0xa3c6281d,0xabc3aadd,0x23c6a81d,0x2bc32add,0x295fa6d7,0x1a482b88,0xa9edab3b,0x2bfe2564,
  0xab882564,0x2b88a564,0xab882564,0x2b88a564,0x2beaa3c6,0xa8c4a81d,0xa0b22bc3,0x2a6daadd,0xaa6d20b2,0xa8c42bea,0x2a6da0b2,0x28c4abea,
  0x26d79a48,0x2b88a9ed,0x2b3babfe,0x2564a95f,0xabfe2bfe,0xabfe2bfe,0xabfe2bfe,0xabfe2bfe,0xaadd2bea,0xa3c628c4,0x281da0b2,0x2bc3aa6d,
  0xa81d2bc3,0x2adda3c6,0x281dabc3,0xaadd23c6,0x9a482b88,0x29edab3b,0xabfe2564,0x295f26d7,0x26d72b3b,0xa6d7ab3b,0x26d72b3b,0xa6d7ab3b,
  0x2a6d2add,0xabeaa3c6,0x28c4a81d,0x20b22bc3,0x2bea2a6d,0xa0b228c4,0xabeaaa6d,0x20b2a8c4,0x2b8829ed,0x2b3b2bfe,0x2564295f,0xa6d79a48,
  0xabfe2bfe,0xabfe2bfe,0xabfe2bfe,0xabfe2bfe,0x2addabea,0x23c6a8c4,0xa81d20b2,0xabc32a6d,0xa81d2bc3,0x2adda3c6,0x281dabc3,0xaadd23c6,
  0x1a48ab88,0xa9ed2b3b,0x2bfea564,0xa95fa6d7,0x26d72b3b,0xa6d7ab3b,0x26d72b3b,0xa6d7ab3b,0xaa6daadd,0x2bea23c6,0xa8c4281d,0xa0b2abc3,
  0x2bea2a6d,0xa0b228c4,0xabeaaa6d,0x20b2a8c4,0xab88a9ed,0xab3babfe,0xa564a95f,0x26d71a48,0x1a489a48,0x1a489a48,0x1a489a48,0x1a489a48,
  0x281da0b2,0x2bc3aa6d,0x2addabea,0x23c6a8c4,0x2adda3c6,0x281dabc3,0xaadd23c6,0xa81d2bc3,0x2bfea564,0xa95fa6d7,0x9a482b88,0x29edab3b,
  0x2b3ba6d7,0xab3b26d7,0x2b3ba6d7,0xab3b26d7,0x28c4a81d,0x20b22bc3,0xaa6daadd,0x2bea23c6,0x20b2a8c4,0x2bea2a6d,0xa0b228c4,0xabeaaa6d,
  0xa564a95f,0x26d71a48,0x2b8829ed,0x2b3b2bfe,0x1a489a48,0x1a489a48,0x1a489a48,0x1a489a48,0xa81d20b2,0xabc32a6d,0xaadd2bea,0xa3c628c4,
  0x2adda3c6,0x281dabc3,0xaadd23c6,0xa81d2bc3,0xabfe2564,0x295f26d7,0x1a48ab88,0xa9ed2b3b,0x2b3ba6d7,0xab3b26d7,0x2b3ba6d7,0xab3b26d7,
  0xa8c4281d,0xa0b2abc3,0x2a6d2add,0xabeaa3c6,0x20b2a8c4,0x2bea2a6d,0xa0b228c4,0xabeaaa6d,0x2564295f,0xa6d79a48,0xab88a9ed,0xab3babfe,
  0xa95fa95f,0xa95fa95f,0xa95fa95f,0xa95fa95f,0xa3c6a8c4,0x281d20b2,0x2bc32a6d,0x2add2bea,0x23c6a81d,0x2bc32add,0xa3c6281d,0xabc3aadd,
  0x295fa6d7,0x1a482b88,0xa9edab3b,0x2bfe2564,0x2b88a564,0xab882564,0x2b88a564,0xab882564,0x2beaa3c6,0xa8c4a81d,0xa0b22bc3,0x2a6daadd,
  0x2a6da0b2,0x28c4abea,0xaa6d20b2,0xa8c42bea,0x26d79a48,0x2b88a9ed,0x2b3babfe,0x2564a95f,0xa95fa95f,0xa95fa95f,0xa95fa95f,0xa95fa95f,
  0x23c628c4,0xa81da0b2,0xabc3aa6d,0xaaddabea,0x23c6a81d,0x2bc32add,0xa3c6281d,0xabc3aadd,0xa95f26d7,0x9a48ab88,0x29ed2b3b,0xabfea564,
  0x2b88a564,0xab882564,0x2b88a564,0xab882564,0xabea23c6,0x28c4281d,0x20b2abc3,0xaa6d2add,0x2a6da0b2,0x28c4abea,0xaa6d20b2,0xa8c42bea,
  0xa6d71a48,0xab8829ed,0xab3b2bfe,0xa564295f,0x29ed29ed,0x29ed29ed,0x29ed29ed,0x29ed29ed,0x2bc32a6d,0x2add2bea,0x23c628c4,0xa81da0b2,
  0x2bc32add,0xa3c6281d,0xabc3aadd,0x23c6a81d,0x29ed2b3b,0xabfea564,0x295fa6d7,0x1a482b88,0x25642b88,0xa564ab88,0x25642b88,0xa564ab88,
  0xa0b22bc3,0x2a6daadd,0xabea23c6,0x28c4281d,0xa8c42bea,0x2a6da0b2,0x28c4abea,0xaa6d20b2,0xab3b2bfe,0xa564295f,0x26d79a48,0x2b88a9ed,
  0x29ed29ed,0x29ed29ed,0x29ed29ed,0x29ed29ed,0xabc3aa6d,0xaaddabea,0xa3c6a8c4,0x281d20b2,0x2bc32add,0xa3c6281d,0xabc3aadd,0x23c6a81d,
  0xa9edab3b,0x2bfe2564,0xa95f26d7,0x9a48ab88,0x25642b88,0xa564ab88,0x25642b88,0xa564ab88,0x20b2abc3,0xaa6d2add,0x2beaa3c6,0xa8c4a81d,
  0xa8c42bea,0x2a6da0b2,0x28c4abea,0xaa6d20b2,0x2b3babfe,0x2564a95f,0xa6d71a48,0xab8829ed,0x9a481a48,0x9a481a48,0x9a481a48,0x9a481a48,
  0xa81d20b2,0xabc32a6d,0xaadd2bea,0xa3c628c4,0xaadd23c6,0xa81d2bc3,0x2adda3c6,0x281dabc3,0xabfe2564,0x295f26d7,0x1a48ab88,0xa9ed2b3b,
  0xab3b26d7,0x2b3ba6d7,0xab3b26d7,0x2b3ba6d7,0xa8c4281d,0xa0b2abc3,0x2a6d2add,0xabeaa3c6,0xa0b228c4,0xabeaaa6d,0x20b2a8c4,0x2bea2a6d,
  0x2564295f,0xa6d79a48,0xab88a9ed,0xab3babfe,0x9a481a48,0x9a481a48,0x9a481a48,0x9a481a48,0x281da0b2,0x2bc3aa6d,0x2addabea,0x23c6a8c4,
  0xaadd23c6,0xa81d2bc3,0x2adda3c6,0x281dabc3,0x2bfea564,0xa95fa6d7,0x9a482b88,0x29edab3b,0xab3b26d7,0x2b3ba6d7,0xab3b26d7,0x2b3ba6d7,
  0x28c4a81d,0x20b22bc3,0xaa6daadd,0x2bea23c6,0xa0b228c4,0xabeaaa6d,0x20b2a8c4,0x2bea2a6d,0xa564a95f,0x26d71a48,0x2b8829ed,0x2b3b2bfe,
  0xabfe2bfe,0xabfe2bfe,0xabfe2bfe,0xabfe2bfe,0xaadd2bea,0xa3c628c4,0x281da0b2,0x2bc3aa6d,0xa81d2bc3,0x2adda3c6,0x281dabc3,0xaadd23c6,
  0x9a482b88,0x29edab3b,0xabfe2564,0x295f26d7,0x26d72b3b,0xa6d7ab3b,0x26d72b3b,0xa6d7ab3b,0x2a6d2add,0xabeaa3c6,0x28c4a81d,0x20b22bc3,
  0x2bea2a6d,0xa0b228c4,0xabeaaa6d,0x20b2a8c4,0x2b8829ed,0x2b3b2bfe,0x2564295f,0xa6d79a48,0xabfe2bfe,0xabfe2bfe,0xabfe2bfe,0xabfe2bfe,
  0x2addabea,0x23c6a8c4,0xa81d20b2,0xabc32a6d,0xa81d2bc3,0x2adda3c6,0x281dabc3,0xaadd23c6,0x1a48ab88,0xa9ed2b3b,0x2bfea564,0xa95fa6d7,
  0x26d72b3b,0xa6d7ab3b,0x26d72b3b,0xa6d7ab3b,0xaa6daadd,0x2bea23c6,0xa8c4281d,0xa0b2abc3,0x2bea2a6d,0xa0b228c4,0xabeaaa6d,0x20b2a8c4,
  0xab88a9ed,0xab3babfe,0xa564a95f,0x26d71a48,0x3bfb3bff,0x3be53bf2,0x3bbf3bd4,0x3b873ba5,0x3bd03bfb,0x3b013b7c,0x399d3a60,0x378538bc,
  0x3a543bcf,0x2884374e,0xb9f8b648,0xbbe9bbab,0x398b3bb7,0xb4db3340,0xbbdcb9fc,0xb911bb85,0x35173b52,0xbbc9b7c8,0xb074ba9b,0x3bfe391b,
  0x319e3b27,0xbbf3b979,0x363cb80a,0x3a2d3bc5,0xb4323a8c,0xb6a4bbf9,0x3b3539b8,0xbbc3ae91,0xb66b3a50,0xad65bbe4,0x38653b90,0xbb0db966,
  0xac6aa5e4,0xb122af59,0xb402b294,0xb56ab4b7,0xb2deac9c,0xb7bdb5a5,0xb9b3b8d6,0xbb10ba73,0xb8e5b2f7,0xbbffbb1e,0xb954bb5c,0x30beb493,
  0xb9c5b43e,0xbb9fbbcb,0xb201b94f,0x3a313576,0xbb96b676,0xb359bafe,0x3bec3884,0x2a163a29,0xbbe0b72c,0x2f27b9d6,0x3b5e3ae8,0xb91633a2,
  0xbbb8b899,0x3b47ad33,0xb6f43999,0xb3babbf5,0xbb54b8ea,0x3bf9313b,0xbab0353a,0x3790b9e7,0x3b3f3b65,0x3ae83b16,0x3a813ab6,0x3a0d3a49,
  0x3263356a,0xad972b43,0xb5dfb359,0xb8eeb7f3,0xb825baa9,0x353aaec3,0x3b7c3994,0x3af43bfa,0x360eb0be,0x3bf43a64,0x388e3b47,0xb7372c6a,
  0xa9b139aa,0xbbedba25,0x3340b889,0x3b983afb,0xbaa2aa16,0xb4cfbb8e,0x3c0038ad,0xb44b38e5,0x38bcb874,0x2ba73bac,0xb979bb59,0x3bf03742,
  0x3c0033ba,0xbb043402,0x3855b974,0xacce3b96,0xb6c6b61a,0xb80ab76f,0xb8a8b85a,0xb93cb8f3,0xbbd7bb87,0xbbf8bbfd,0xbb71bbc9,0xba4dbaf1,
  0x3ad8386f,0x3b903bf5,0x35a539bc,0xb7e8ad00,0x3b683be9,0x2ef538d1,0xba93b6a4,0xbb24bbfb,0xbbfeb9a6,0x305bb91f,0x3bcb3a97,0xb50b37d2,
  0xb87abbfe,0x3ba13546,0x24523a7e,0xbbb5ba54,0x3a733aa5,0xbbfcb487,0x39d6b654,0xafef3b21,0x1cb63bc3,0xb7b2bbbf,0x3aba39da,0xbbfab517,
  0x398b39cd,0x38fd3946,0x386538b2,0x37853815,0xba85b9c9,0xbb92bb1e,0xbbfebbdd,0xbbc2bbf5,0x319e389e,0xb929b426,0xbc00bb45,0xb911bb37,
  0xbbffbac1,0xb805bafe,0x382a217f,0x3bfd3b13,0xb66b3682,0xbb01bb94,0x387fb371,0x3a2d3beb,0xbac7bb76,0x3a00ad33,0x36bb3bd4,0xbbeab79b,
  0xbabd330f,0x34dbba58,0x36023bfe,0xbb0db9f4,0xb68dbbe1,0x3a5c3a45,0xbbe7b648,0x3b89adfb,0xb9c5b982,0xba41ba04,0xbab0ba7a,0xbb10bae1,
  0xb8a3b986,0xb52fb74e,0xa94db1e8,0x33d32e91,0xbbe0ba89,0xba1dbbba,0x1fdbb6af,0x3a3136e8,0xa776b84a,0x3aeb37c8,0x3ad53c00,0xaa7a377a,
  0xbb54bb4f,0x37bdb523,0x3a9e3bc8,0xb916308d,0x3840b5c8,0x394a3bf9,0xbb42b294,0xb0a6bb0a,0xb850bbce,0x3b9f38e0,0xbb6a28e8,0x3790b958,
  0x3b4cb185,0xb8db38f8,0x30f0bb5c,0x355e3bf7,0x363136dd,0x34cf3581,0x32c6341a,0x2fbd3153,0xbae1bb65,0xb970ba39,0xb715b889,0xb16cb4f3,
  0x3219b3d3,0x3b0438b7,0x3b713bfc,0x34ff397d,0x36e83aa9,0xb8b2adc9,0xbbefbb59,0xb5bcba49,0xb9a12a7a,0xb924bbfe,0x3a933042,0x37dd3bcc,
  0x308db9aa,0x3b453b07,0xb94632ad,0xb845bbfa,0x3bd730a6,0xb902382a,0xa452bb92,0x39373b7a,0xb9583874,0x3371bb16,0x34263c00,0xb982bafb,
  0xbb60bb3a,0xbba1bb83,0xbbd2bbbc,0xbbf1bbe3,0x3815361a,0x39df3907,0x3b2c3a97,0x3be23b9c,0x3bda3bc2,0x37b23a76,0xb5df2c06,0xbb9ab9d2,
  0xbb37b86f,0xba7abbf8,0x3029b654,0x3b7838f3,0xb9afbbfd,0x3a21294d,0x388e3bee,0xbaf7b328,0x3beb39a6,0xb6af37a6,0xba04bbd3,0x3ac42d00,
  0x32633bea,0xba3dbad5,0x3c00352f,0xba1135b1,0xb9f4baa5,0x3bc8376f,0xbbba2311,0x39cdb7d2,0x3b7a3bf1,0x394a3a93,0x33893764,0xb3d39cb6,
  0x3afb3be2,0x35eb3946,0xb4c328e8,0xbaa9b8cc,0x38a33b9a,0xb8dba452,0xbb83bbae,0x2a7ab86a,0x37423b78,0xbab6b426,0xb907bbe6,0x39aa2ade,
  0x27763af7,0xbb2fbaba,0x3a76ad97,0x30a63b60,0xaf8b3ac4,0xb994bb94,0x3bf8358d,0xb8743815,0xb8403a11,0x341abb57,0x294d3bf4,0xb55ebbda,
  0xb93339cd,0x3889ba58,0xb7a63ad1,0x3625bb37,0xb5b1afbd,0xba00b88e,0xbbc6bb18,0xbbc2bc00,0xb7d2b16c,0xbb6fba04,0xbba3bbfe,0xb86fba67,
  0xba85b4ff,0xba5cbc00,0x3581b47b,0x3bfd3aac,0xbb21b5bc,0xb85abbba,0x3a393109,0x39a63bfd,0xbbffb7dd,0x370ab855,0x38b73bf8,0xbbeab631,
  0xbbf2b845,0x39bcb523,0x2dc93b81,0xbaa5bae1,0xbac7b937,0x3bbc365f,0xbbfeaef5,0x3b89b219,0xba15b982,0x3a9738e0,0xbb07b830,0x3b6336e8,
  0xb958b785,0xbb81ba9e,0xbbefbbf3,0xba89bb73,0xbbf7bbc2,0xb9b8bb42,0xaf59b70a,0x384a3328,0x3bc03911,0x38303b6a,0xb946ad65,0xbb4fbbd0,
  0x3a353bfd,0xb85f30f0,0xbb1ebbbc,0x35c8b5b1,0xbb8bba2d,0x39dfb27c,0x34263bb0,0xbbceb98b,0xb4b7bbea,0x3b6c39e3,0xbafe2c06,0x3185ba85,
  0x38cc3b0d,0xba7ab99d,0x3b943759,0xbbffb19e,0xb4933b89,0x31e8bbc6,0xad333bee,0xa5e4bbff,0xb9f4bb10,0xb58db87f,0x3029af27,0x389e35d4,
  0x2dfbb3d3,0x399936bb,0x3bf23b2f,0x3ac13bcc,0x33eb3a31,0xbad1b602,0xba04bbf9,0x3682b2de,0xb90c2a7a,0xbab3bbe7,0x374eb41a,0x3b763b7a,
  0x3552b916,0x39703bd6,0xbbbab46f,0x330fb9c5,0x3ba530a6,0xb5f7396b,0xb7c8bbfc,0x3be138a3,0xba673790,0x38b2b9b3,0xb5233b1b,0x26adbbe0,
  0xbbabb55e,0x3bdd3389,0xbbf9b042,0x3bff2776,0xb742b93c,0x2311b340,0x37a6340e,0x3aa93966,0x3b963a4d,0x3b7f3c00,0x380f3a21,0xb0be3219,
  0x2f8bb7e8,0x3bde3979,0x376f3b32,0xb9aab0d7,0x3bb83b24,0xb1223855,0xbbfdba3d,0xaa16b9a1,0x3933b50b,0x35eb3be4,0xbbf5b8d6,0x3874b6c6,
  0x39413bb5,0xbbffb65f,0x38d1b764,0x33ba3bd7,0x3bb3afef,0xbab63699,0x391fb94f,0xb6253ad8,0x30103bfa,0xb359bbdf,0x35463bae,0xb6d2bb68,
  0x3b213a0d,0x3c003bcb,0x3b073bbd,0x386f39e7,0x351738ee,0xb599a452,0xbae5b924,0xbbe9bbda,0x3bf23af4,0x31cf39d6,0xbb16b6ff,0xb9a6bbe8,
  0xb4323737,0xbbe5baba,0x2b43b902,0x3bfe39af,0x3a153b98,0xbb6fb13b,0x2ec3ba60,0x3aa53b3f,0xba09344b,0xa884bb57,0x3a643b18,0xbbc3b263,
  0x34573bf0,0xb85abb4a,0x3a2539fc,0xbb63b825,0xbbef2cce,0x3bc9b1b6,0xbb8e347b,0x3b3db60e,0x3bf53b87,0x3b6c3bec,0x392e3a7e,0x32f73721,
  0xb9e7b785,0xbbfcbb5e,0xba81bbb0,0xb43eb894,0xbb13bbe9,0x31e8b6f4,0x3bf239da,0x36763af1,0x3be83911,0x340e3ab0,0xbb7cb759,0xb72cbb73,
  0x379b3bfe,0xbc00b80f,0x374eb835,0x38993bfb,0xbb3fba2d,0x3b329fdb,0xb3403a41,0xb8eabbd0,0x2dfbbbc3,0x32943bfd,0xb7c8bb7f,0x39c93a54,
  0x38253b0d,0xb8d6ba9e,0x39793a1d,0xba0db98b,0x2e91356a,0xb5f7b074,0xba19b8ad,0xbbcfbb2a,0xb966bb10,0xaba7b63c,0x38a8346f,0x3bb73a90,
  0x377ab0be,0x3bdd3b35,0x2f593974,0xbb52b7f3,0x30d73a31,0xbbbdb865,0xb5a5bb1b,0x3b2735d4,0xbb0aaa16,0xa17fbae5,0x3b1e3ace,0xba8c2c6a,
  0x36c6b916,0x36ff3c00,0xbbcbb8fd,0x3a50b2de,0x3bf733ba,0xbbd42b43,0x3afeb599,0xb98638e5,0xbad83790,0x3a60b87f,0xb9d63929,0x393cb9c5,
  0xba093986,0x3a7eb8f8,0xbae5385f,0x3b3db77a,0xbabd393c,0x3bb0b699,0xbc00305b,0x3ba730d7,0xbbef384a,0x39da34e7,0x2b43bb6c,0xba6f3b0a,
  0xbc0037e8,0x3759383a,0x387fbbfc,0xbbf636c6,0xbb2a35c8,0xb8353bb2,0x3a64b1e8,0x3962bbf7,0xba90350b,0xba413bff,0x3602340e,0x3bf6bad8,
  0xb7f33185,0xbb7f3a19,0xbb8e3c00,0xb8203a35,0xb5d42fef,0xba1d38a8,0xbbd63b32,0xbba93bfe,0xb941b9c9,0x38ad3a45,0xb80fbab3,0x36d23b13,
  0xb850ba0d,0x346f3b4a,0x1fdbbbed,0xb4ab3be8,0xb010bac1,0xb9743b9e,0x3bfdb5f7,0xb8c1b79b,0x251bbaf4,0xbb1b3acb,0x3a9e2ba7,0x2e5fbb3f,
  0x3721bb76,0xbace3463,0xb8d13bdd,0x39ebadfb,0x3894bb98,0xb8fd281f,0xbb6a3bbd,0x2e2d3825,0x3af1bbe1,0x3599b92e,0xb546a17f,0xbadb390c,
  0x3b73bbf0,0x3929ba81,0x327cb6ff,0xb49f29b1,0xbb853625,0x3bbdb4c3,0xbbe432ad,0x3bfbaf8b,0xbaacb6d2,0x39243954,0xb65fbace,0x2fbd3bb8,
  0x3bc5b24b,0xb6ffb907,0xb6993c00,0x3bb7b933,0x363138c1,0x3902bbec,0xbbdf3599,0x34ff3941,0xb9661648,0xba603bf8,0x383a31cf,0x3b27bbb3,
  0x3219b9eb,0xbb1836f4,0xb9903be5,0x37dd3010,0x30d73232,0x39fcb7a6,0x3bffbb6f,0x3a50bb9c,0xb9a13adb,0xb47b380f,0x32c62884,0x3937b721,
  0xb576bb63,0x340e3ba3,0xb13bbbd3,0x2c9c3bf2,0x386abb3d,0xba2139f8,0x3b57b835,0xbbf13432,0xb3a23bd8,0x3b32ba39,0xbb4a2311,0x343e3a15,
  0xbb603a6f,0x3a3d3074,0x31b6bb7f,0xbb9a3a09,0x39e7bc00,0xb8d6adc9,0xbacb3bde,0x372c3457,0x3bdab962,0x3764bb35,0xb9c03122,0xbaf73bef,
  0xbbe83bd9,0xb94f3b07,0xa81f35eb,0x38eab4f3,0xb9af3820,0xbbae3ae5,0xbbd23bff,0xba113b2a,0xbc0026ad,0x3bf32c38,0xbbd6b109,0x3ba733eb,
  0x3153bbff,0xb70a3b9e,0x396bba9b,0xbade390c,0xba90b16c,0x2d653aee,0x39b3bb81,0xbbf63552,0x397dbbcf,0xbbbc3463,0x338939b8,0x39f0bba5,
  0xb5d4b5bc,0xbbb03b2c,0x32013830,0x3bf6ba67,0x3bccbb52,0x2c06b92e,0xbb83385f,0xb8c73bab,0x32deb845,0xb7593029,0xbb5e39df,0xbba93bfd,
  0x3b7aba8c,0x3beebbf2,0x3a76bb6c,0x36ddb91b,0x251bbbff,0xaf273bfc,0x327cbbe6,0xb4ab3bc0,0x3be325e4,0xbb2fb4e7,0x39e33884,0xb81aba35,
  0x3894bbe2,0xbbf937fe,0x399d358d,0x2e5fbb8b,0x39d232f7,0x341abbb2,0xbbc63999,0x395d34b7,0x3b73bb78,0xb46fb715,0xbbdc3ad1,0x2e2d38cc,
  0x33283676,0x3bfcba19,0x3581bab3,0xba6b3493,0x3bd0bac4,0x3b1bbbef,0x363cb970,0xb49faade,0xb5b13899,0x30422f59,0x38b7b5f7,0x3b3aba29,
  0xbb68b55e,0x3b1836bb,0xbabab805,0x3a4d38a3,0x3bc0b625,0xbbfe2ec3,0x3b9431cf,0xba89b742,0x387a381a,0x347bbbe7,0xbb573a00,0x3b242776,
  0xbb8b324b,0x31093a25,0x3a58bb6f,0xbb4f2f8b,0x9cb6b95d,0xbbf8396b,0xb1b63a5c,0x3bb5b840,0x38cc9648,0x3b81bbac,0xac38b85a,0xbbce3933,
  0xb86a3a6b,0x2ef53389,0x39c0b70a,0x3bfabb4c,0xaadeb232,0xb83034c3,0xbaee39bc,0xbbff3bb3,0x360ebb89,0xb7643b42,0x3855baeb,0xb8ee3a85,
  0x33eb3b63,0x28e8bbf5,0xb5233bde,0x389ebb21,0xbaa23ade,0x3baeb0f0,0xb65fb94a,0xb7373bff,0x3552bbd8,0xbbe6391f,0x38e035eb,0x3682bbf2,
  0x3c00b9f0,0x2d97b9e3,0xbbdf38db,0xb44b3ac7,0xba673c00,0x358d3487,0x3bfcbab6,0x330fba15,0xbaac38c7,0xbbf43bc6,0xb9903b2f,0xacce368d,
  0x3bfdbbd9,0x3ad1bba3,0x37feb994,0x26adb457,0xbb4c38ee,0x3bfcb1b6,0xbad5b4cf,0x381a39af,0xbbb3389e,0x3b592c38,0xb76fb970,0xb24b3beb,
  0xbbe33737,0x304239c0,0x3b42bb04,0xb95db263,0xbb9c3682,0xb2ad3aee,0x3bf5b8b2,0x1648b9f4,0xb9d2344b,0xbb923bd2,0xb0f03924,0x3a6bb60e,
  0xb8f3330f,0xbc003b2c,0xb91f3b45,0x323233eb,0xb3282cce,0xb80535df,0xb9e33902,0xbb3a3aa2,0xad0026ad,0xb1cf3029,0xb4873371,0xb61a3552,
  0xb68dba4d,0xac063bdf,0x382abba1,0xbade39a1,0xb457ba89,0xb6543bfc,0x3b16b9df,0xbbd8308d,0x3153bb24,0xbbee3990,0x36bb37b2,0x39f0bbd7,
  0x34f3bb4f,0xbbd337fe,0xaec33a7a,0x3c00b958,0x397dbbb5,0xb52fb2c6,0xbbe73a21,0xb8c73b68,0x3a49bbce,0x2311b715,0xba2536af,0xbbd93bc0,
  0x3bccbbfa,0x3aebbb71,0x396bba3d,0x36ddb87a,0x3bfabbff,0x3bdebbef,0x3bacbbc8,0x3b65bb8b,0xaadebba7,0xb6af3bdc,0x3a58ba41,0xbbe2366b,
  0x3a29bade,0xbc003581,0x3a45352f,0xb2f7bac7,0xb8153bf6,0x3bc8b63c,0xac38ba1d,0xbb783abd,0xbbf539f0,0x329438b7,0x3b9ebaeb,0xb676b68d,
  0x3b37bbf6,0x28e8b865,0xbaee37bd,0xbac43c00,0x3b13b8c7,0x3b5cbbfe,0x3463b94a,0xb8993153,0xbbeb3ba9,0xbbe63c00,0xbb2c3b9f,0xb9cd3a90,
  0xb79b36dd,0xb884382a,0xb92e38db,0xb9c9397d,0x3bfdb4ab,0xbb45b201,0x38e038fd,0xb16cbb54,0x391b381a,0xa17fbb83,0xb8f83b92,0x3bcfb840,
  0xbae12e5f,0xb3713b5e,0x3bfcb929,0xb5bcb850,0xae91b95d,0xbbd43a76,0x34e73805,0x3b52bb4c,0x36e82e2d,0x3bfebab0,0x37febb01,0xb845251b,
  0xb77a3a6b,0x3648294d,0x3bb2ba00,0x3a8cbbe3,0x308db49f,0xb1091fdb,0xb71534db,0xb9823894,0x3b0abb3a,0x3a9bbad5,0x3a19ba5c,0x3986b9d2,
  0x3b9c2c9c,0xb994b83a,0x34873ae8,0x324bbbfe,0xb7213bf1,0x3b47b990,0xbbbf2d97,0x38c1387a,0x38f3343e,0x3889bbff,0xbba3353a,0x96483a73,
  0xbaf13b9a,0x38ad32c6,0x39f8bbf4,0xb9eb9cb6,0x2d00372c,0x3b59b8a8,0x3a39bbed,0xb232b576,0xbbfb3af7,0xb9743b71,0x307434cf,0x3adbb86a,
  0xb7d238ea,0xb2ad35a5,0x2dc92ba7,0x361ab3a2,0xba543a11,0xbace3a93,0xbb353b04,0xbb873b60,0xb4f33bfb,0x39bcbacb,0xbbac380a,0x3bd8a9b1,
  0xbb2aafbd,0x36a439c0,0x3402bbf8,0xba6f3aa2,0xba493bb7,0x3a97a81f,0x34c3bb90,0xbc0038bc,0xb7f3b4ff,0xba7e3bd2,0x39542ef5,0x3962bc00,
  0xbbfa3b27,0xb6543a81,0x3907b05b,0x3bd9bb85,0x2c6ab7dd,0xb9da35df,0xbbec3ba1,0xb8203aac,0xbafb3a50,0xbbd33b7c,0xbbf83bfc,0xbb653bc5,
  0x38e5b937,0x3835b88e,0x36f4b7b2,0x356ab631,0xb90c3b3d,0x3b5cb8d1,0xbbf93122,0x3ac13517,0x29b1bba7,0xb94f3b6a,0x3be4b7bd,0xbaf4b19e,
  0x3ba5ba6f,0xb884b546,0xb8f83bff,0x3b76b432,0xb8bc3bf6,0x3ae8b27c,0x3699bb9f,0xbb98366b,0xbbab3962,0xb9993bbf,0x34e73359,0x3be1ba09,
  0x3b85bbf6,0x353ab99d,0xb83a2f27,0xbbf03abd,0x391bb820,0x3ab3b9f8,0x3bb2bb47,0x3bffbbef,0xbbc53ba9,0xbbed3bdc,0xbbff3bf9,0xbbfb3c00,
  0xba35b6d2,0x36483a64,0x2d33bbe5,0xb84a3b96,0x3bfeb4ab,0xb9fcb602,0x313b3b01,0x37e8bbe0,0x34b738c1,0x3a9bbb8e,0xba45a884,0xb5c83bb8,
  0xba732e5f,0xb80a3bd6,0x3b4ab4db,0x350bbb54,0x3493b9eb,0xb9b83402,0xbb9e3bc9,0xb1853941,0x35762e2d,0x3b90b9b3,0x3acbbbf3,0x2fefb850,
  0xba293adb,0xb85f3954,0xb46336a4,0x25e43010,0x33a2b49f,0x305bb201,0x281fad65,0xac9c251b,0x3f803f80,0x3f803f80,0x3f803f80,0x3f803f80,
  0x3f803f80,0x3f803f80,0x3f803f80,0x3f803f80,0x3f803f80,0x3f803f80,0x3f803f80,0x3f803f80,0x3f803f80,0x3f803f80,0x3f803f80,0x3f803f80,
  0x3f803f80,0x3f803f80,0x3f803f80,0x3f803f80,0x3f803f80,0x3f803f80,0x3f803f80,0x3f803f80,0x3f803f80,0x3f803f80,0x3f803f80,0x3f803f80,
  0x3f803f80,0x3f803f80,0x3f803f80,0x3f803f80,0x3f803f80,0x3f803f80,0x3f803f80,0x3f803f80,0x3f803f80,0x3f803f80,0x3f803f80,0x3f803f80,
  0x3f803f80,0x3f803f80,0x3f803f80,0x3f803f80,0x3f803f80,0x3f803f80,0x3f803f80,0x3f803f80,0x3f803f80,0x3f803f80,0x3f803f80,0x3f803f80,
  0x3f803f80,0x3f803f80,0x3f803f80,0x3f803f80,0x3f803f80,0x3f803f80,0x3f803f80,0x3f803f80,0x3f803f80,0x3f803f80,0x3f803f80,0x3f803f80,
  0x3f803f80,0x3f803f80,0x3f803f80,0x3f803f80,0x3f803f80,0x3f803f80,0x3f803f80,0x3f803f80,0x3f803f80,0x3f803f80,0x3f803f80,0x3f803f80,
  0x3f803f80,0x3f803f80,0x3f803f80,0x3f803f80,0x3f803f80,0x3f803f80,0x3f803f80,0x3f803f80,0x3f803f80,0x3f803f80,0x3f803f80,0x3f803f80,
  0x3f803f80,0x3f803f80,0x3f803f80,0x3f803f80,0x3f803f80,0x3f803f80,0x3f803f80,0x3f803f80,0x3f803f80,0x3f803f80,0x3f803f80,0x3f803f80,
  0x3f803f80,0x3f803f80,0x3f803f80,0x3f803f80,0x3f803f80,0x3f803f80,0x3f803f80,0x3f803f80,0x3f803f80,0x3f803f80,0x3f803f80,0x3f803f80,
  0x3f803f80,0x3f803f80,0x3f803f80,0x3f803f80,0x3f803f80,0x3f803f80,0x3f803f80,0x3f803f80,0x3f803f80,0x3f803f80,0x3f803f80,0x3f803f80,
  0x3f803f80,0x3f803f80,0x3f803f80,0x3f803f80,0x3f803f80,0x3f803f80,0x3f803f80,0x3f803f80,0x3f803f80,0x3f803f80,0x3f803f80,0x3f803f80,
  0x3f803f80,0x3f803f80,0x3f803f80,0x3f803f80,0x3f803f80,0x3f803f80,0x3f803f80,0x3f803f80,0x3f803f80,0x3f803f80,0x3f803f80,0x3f803f80,
  0x3f803f80,0x3f803f80,0x3f803f80,0x3f803f80,0x3f803f80,0x3f803f80,0x3f803f80,0x3f803f80,0x3f803f80,0x3f803f80,0x3f803f80,0x3f803f80,
  0x3f803f80,0x3f803f80,0x3f803f80,0x3f803f80,0x3f803f80,0x3f803f80,0x3f803f80,0x3f803f80,0x3f803f80,0x3f803f80,0x3f803f80,0x3f803f80,
  0x3f803f80,0x3f803f80,0x3f803f80,0x3f803f80,0x3f803f80,0x3f803f80,0x3f803f80,0x3f803f80,0x3f803f80,0x3f803f80,0x3f803f80,0x3f803f80,
  0x3f803f80,0x3f803f80,0x3f803f80,0x3f803f80,0x3f803f80,0x3f803f80,0x3f803f80,0x3f803f80,0x3f803f80,0x3f803f80,0x3f803f80,0x3f803f80,
  0x3f803f80,0x3f803f80,0x3f803f80,0x3f803f80,0x3f803f80,0x3f803f80,0x3f803f80,0x3f803f80,0x3f803f80,0x3f803f80,0x3f803f80,0x3f803f80,
  0x3f803f80,0x3f803f80,0x3f803f80,0x3f803f80,0x3f803f80,0x3f803f80,0x3f803f80,0x3f803f80,0x3f803f80,0x3f803f80,0x3f803f80,0x3f803f80,
  0x3f803f80,0x3f803f80,0x3f803f80,0x3f803f80,0x3f803f80,0x3f803f80,0x3f803f80,0x3f803f80,0x3f803f80,0x3f803f80,0x3f803f80,0x3f803f80,
  0x3f803f80,0x3f803f80,0x3f803f80,0x3f803f80,0x3f803f80,0x3f803f80,0x3f803f80,0x3f803f80,0x3f803f80,0x3f803f80,0x3f803f80,0x3f803f80,
  0x3f803f80,0x3f803f80,0x3f803f80,0x3f803f80,0x3f803f80,0x3f803f80,0x3f803f80,0x3f803f80,0x3f803f80,0x3f803f80,0x3f803f80,0x3f803f80,
  0x3f803f80,0x3f803f80,0x3f803f80,0x3f803f80,0x3f803f80,0x3f803f80,0x3f803f80,0x3f803f80,0x3f803f80,0x3f803f80,0x3f803f80,0x3f803f80,
  0x3f803f80,0x3f803f80,0x3f803f80,0x3f803f80,0x3f803f80,0x3f803f80,0x3f803f80,0x3f803f80,0x3f803f80,0x3f803f80,0x3f803f80,0x3f803f80,
  0x3f803f80,0x3f803f80,0x3f803f80,0x3f803f80,0x3f803f80,0x3f803f80,0x3f803f80,0x3f803f80,0x3f803f80,0x3f803f80,0x3f803f80,0x3f803f80,
  0x3f803f80,0x3f803f80,0x3f803f80,0x3f803f80,0x3f803f80,0x3f803f80,0x3f803f80,0x3f803f80,0x3f803f80,0x3f803f80,0x3f803f80,0x3f803f80,
  0x3f803f80,0x3f803f80,0x3f803f80,0x3f803f80,0x3f803f80,0x3f803f80,0x3f803f80,0x3f803f80,0x3f803f80,0x3f803f80,0x3f803f80,0x3f803f80,
  0x3f803f80,0x3f803f80,0x3f803f80,0x3f803f80,0x3f803f80,0x3f803f80,0x3f803f80,0x3f803f80,0x3f803f80,0x3f803f80,0x3f803f80,0x3f803f80,
  0x3f803f80,0x3f803f80,0x3f803f80,0x3f803f80,0x3f803f80,0x3f803f80,0x3f803f80,0x3f803f80,0x3f803f80,0x3f803f80,0x3f803f80,0x3f803f80,
  0x3f803f80,0x3f803f80,0x3f803f80,0x3f803f80,0x3f803f80,0x3f803f80,0x3f803f80,0x3f803f80,0x3f803f80,0x3f803f80,0x3f803f80,0x3f803f80,
  0x3f803f80,0x3f803f80,0x3f803f80,0x3f803f80,0x3f803f80,0x3f803f80,0x3f803f80,0x3f803f80,0x3f803f80,0x3f803f80,0x3f803f80,0x3f803f80,
  0x3f803f80,0x3f803f80,0x3f803f80,0x3f803f80,0x3f803f80,0x3f803f80,0x3f803f80,0x3f803f80,0x3f803f80,0x3f803f80,0x3f803f80,0x3f803f80,
  0x3f803f80,0x3f803f80,0x3f803f80,0x3f803f80,0x3f803f80,0x3f803f80,0x3f803f80,0x3f803f80,0x3f803f80,0x3f803f80,0x3f803f80,0x3f803f80,
  0x3f803f80,0x3f803f80,0x3f803f80,0x3f803f80,0x3f803f80,0x3f803f80,0x3f803f80,0x3f803f80,0x3f803f80,0x3f803f80,0x3f803f80,0x3f803f80,
  0x3f803f80,0x3f803f80,0x3f803f80,0x3f803f80,0x3f803f80,0x3f803f80,0x3f803f80,0x3f803f80,0x3f803f80,0x3f803f80,0x3f803f80,0x3f803f80,
  0x3f803f80,0x3f803f80,0x3f803f80,0x3f803f80,0x3f803f80,0x3f803f80,0x3f803f80,0x3f803f80,0x3f803f80,0x3f803f80,0x3f803f80,0x3f803f80,
  0x3f803f80,0x3f803f80,0x3f803f80,0x3f803f80,0x3f803f80,0x3f803f80,0x3f803f80,0x3f803f80,0x3f803f80,0x3f803f80,0x3f803f80,0x3f803f80,
  0x3f803f80,0x3f803f80,0x3f803f80,0x3f803f80,0x3f803f80,0x3f803f80,0x3f803f80,0x3f803f80,0x3f803f80,0x3f803f80,0x3f803f80,0x3f803f80,
  0x3f803f80,0x3f803f80,0x3f803f80,0x3f803f80,0x3f803f80,0x3f803f80,0x3f803f80,0x3f803f80,0x3f803f80,0x3f803f80,0x3f803f80,0x3f803f80,
  0x3f803f80,0x3f803f80,0x3f803f80,0x3f803f80,0x3f803f80,0x3f803f80,0x3f803f80,0x3f803f80,0x3f803f80,0x3f803f80,0x3f803f80,0x3f803f80,
  0x3f803f80,0x3f803f80,0x3f803f80,0x3f803f80,0x3f803f80,0x3f803f80,0x3f803f80,0x3f803f80,0x3f803f80,0x3f803f80,0x3f803f80,0x3f803f80,
  0x3f803f80,0x3f803f80,0x3f803f80,0x3f803f80,0x3f803f80,0x3f803f80,0x3f803f80,0x3f803f80,0x3f803f80,0x3f803f80,0x3f803f80,0x3f803f80,
  0x3f803f80,0x3f803f80,0x3f803f80,0x3f803f80,0x3f803f80,0x3f803f80,0x3f803f80,0x3f803f80,0x3f803f80,0x3f803f80,0x3f803f80,0x3f803f80,
  0x3f803f80,0x3f803f80,0x3f803f80,0x3f803f80,
};

__device__ __align__(128) float    g_part[16][8][2176];
__device__ __align__(128) float    g_kv[16][2176];
constexpr int OBLK = 16 * 1024 + 32;
__device__ __align__(128) uint4    g_o[16 * OBLK];
#define GSTAMP(role, i) do {} while (0)
#define STAMP(role, i) do {} while (0)
#define PDUMP(role) do {} while (0)
#define PROF_SMEM 0

constexpr int STAGE_BYTES = 57344;
constexpr int OFF_H = 4 * 16384, OFF_VP = 9 * 16384, OFF_SPARE = 10 * 16384;
constexpr int OFF_XT = 172032, XT_STRIDE = 4112;
constexpr int OFF_BAR = 204928, OFF_EPOCH = OFF_BAR + 640, OFF_EX = OFF_BAR + 656, OFF_D = OFF_BAR + 672, OFF_SCALE = OFF_BAR + 704;
constexpr int OFF_F2F = 205824, OFF_F2I = 207872, OFF_F4 = 209920, OFF_ONES = 214016, OFF_KVB = 214016;
constexpr int OFF_STG = 219136, STG_STRIDE = 4352, SMEM_TOTAL = 232192 + PROF_SMEM;
enum { B_FULL1 = 0, B_EMPTY1 = 3, B_Q = 6, B_ODONE1 = 7, B_O1RDY = 8, B_H = 9, B_XRAW = 10, B_XT = 11, B_KV = 12, B_Y = 13,  B_AFREE = 15,
       B_STG = 18, B_ODONE = 24, B_XFREE = 25, B_FULL2 = 33, B_CONS2 = 49, B_SFREE = 14, B_KV1 = 61, B_OLOC = 60, B_PKRDY = 62, B_PKFREE = 64, B_H2 = 65, B_G1DONE = 66, B_COUNT = 67, B_FIRST = 67 };
constexpr uint64_t SLOT_A = 0x6859468594685948ull, SLOT_B = 0x7103271032710326ull;
constexpr int NPRE = 6, BEARLY = 3;
__host__ __device__ constexpr int bar_count(int i) {
  return i < B_EMPTY1 ? 1 : i < B_Q ? 4 : i == B_XT ? 4 : i == B_H ? 4 : (i == B_SFREE || i == B_G1DONE) ? 2 : i >= B_PKFREE ? 4 : i >= B_PKRDY ? 8 : i == B_Y ? 9
       : (i >= B_AFREE && i < B_STG) ? 16 : (i == B_ODONE || i == B_ODONE1) ? 8 : (i >= B_XFREE && i < B_FULL2) ? 4
       : i == B_KV1 ? 1 : i == B_OLOC ? 2 : i >= B_CONS2 ? 4 : (i >= B_FULL2 && i < B_FULL2 + NPRE) ? 2 : 1;
}
__host__ __device__ constexpr uint64_t bar_counts(int r) {
  uint64_t v = 0;
  for (int w = 0; w < 11; w++) v |= (uint64_t)(bar_count(1 + 11 * r + w) - 1) << (4 * w);
  return v;
}
constexpr uint32_t SW128 = 64 | (1u << 30);
constexpr int SPIN_LIMIT = 1 << 22;
#define OLOC 1
#define G2E 1
#define G2P 1
#define RC 200
#define PFD 3
#define PD1 700
#define PD2 450
#define QPF 6
#define BPACE 250
#define OCH 3
#define O1D 0
#define HOLD2 12
#define D1 100
#define TRICK 3
#define HSTART 1500
#define PACE 800

__device__ __forceinline__ uint32_t smem_u32(const void* p) { return (uint32_t)__cvta_generic_to_shared(p); }
__device__ __forceinline__ void wg_fence() { asm volatile("wgmma.fence.sync.aligned;" ::: "memory"); }
__device__ __forceinline__ void wg_commit() { asm volatile("wgmma.commit_group.sync.aligned;" ::: "memory"); }
template <int N> __device__ __forceinline__ void wg_wait() { asm volatile("wgmma.wait_group.sync.aligned %0;" ::"n"(N) : "memory"); }
template <int N> __device__ __forceinline__ void keep(float (&d)[N]) {
#pragma unroll
  for (int i = 0; i < N; i++) asm volatile("" : "+f"(d[i])::"memory");
}
__device__ __forceinline__ void mbar_init(uint32_t bar, int cnt) { asm volatile("mbarrier.init.shared::cta.b64 [%0], %1;" ::"r"(bar), "r"(cnt)); }
__device__ __forceinline__ void mbar_expect(uint32_t bar, int bytes) { asm volatile("mbarrier.arrive.expect_tx.shared::cta.b64 _, [%0], %1;" ::"r"(bar), "r"(bytes) : "memory"); }
__device__ __forceinline__ void mbar_arrive(uint32_t bar) { asm volatile("mbarrier.arrive.shared::cta.b64 _, [%0];" ::"r"(bar) : "memory"); }
__device__ __forceinline__ void mbar_arrive_cl(uint32_t bar, uint32_t cta) {
  asm volatile("{\n.reg .b32 r;\nmapa.shared::cluster.u32 r, %0, %1;\nmbarrier.arrive.shared::cluster.b64 _, [r];\n}\n" ::"r"(bar), "r"(cta) : "memory");
}
__device__ __forceinline__ void mbar_wait(uint32_t bar, uint32_t parity) {
  asm volatile("{\n.reg .pred p;\n.reg .u32 n;\nmov.u32 n, 0;\n"
               "W_%=:\nmbarrier.try_wait.parity.shared::cta.b64 p, [%0], %1;\n@p bra D_%=;\n"
               "add.u32 n, n, 1;\nsetp.lt.u32 p, n, %2;\n@p bra W_%=;\ntrap;\nD_%=:\n}\n" ::"r"(bar), "r"(parity), "n"(SPIN_LIMIT) : "memory");
}
__device__ __forceinline__ void fence_async() { asm volatile("fence.proxy.async.shared::cta;" ::: "memory"); }
__device__ __forceinline__ void bar_sync(int id) { asm volatile("bar.sync %0, 128;" ::"r"(id) : "memory"); }
__device__ __forceinline__ void tma2d(uint32_t dst, const CUtensorMap* m, int c0, int c1, uint32_t bar) {
  asm volatile("cp.async.bulk.tensor.2d.shared::cluster.global.mbarrier::complete_tx::bytes [%0], [%1, {%3, %4}], [%2];"
               ::"r"(dst), "l"(m), "r"(bar), "r"(c0), "r"(c1) : "memory");
}
__device__ __forceinline__ void tma2d_mc(uint32_t dst, const CUtensorMap* m, int c0, int c1, uint32_t bar) {
  asm volatile("cp.async.bulk.tensor.2d.shared::cluster.global.mbarrier::complete_tx::bytes.multicast::cluster [%0], [%1, {%3, %4}], [%2], %5;"
               ::"r"(dst), "l"(m), "r"(bar), "r"(c0), "r"(c1), "h"((uint16_t)3) : "memory");
}
__device__ __forceinline__ void tma3d(uint32_t dst, const CUtensorMap* m, int c0, int c1, int c2, uint32_t bar) {
  asm volatile("cp.async.bulk.tensor.3d.shared::cluster.global.mbarrier::complete_tx::bytes [%0], [%1, {%3, %4, %5}], [%2];"
               ::"r"(dst), "l"(m), "r"(bar), "r"(c0), "r"(c1), "r"(c2) : "memory");
}
__device__ __forceinline__ void tma4d(uint32_t dst, const CUtensorMap* m, int c0, int c1, int c2, int c3, uint32_t bar) {
  asm volatile("cp.async.bulk.tensor.4d.shared::cluster.global.mbarrier::complete_tx::bytes [%0], [%1, {%3, %4, %5, %6}], [%2];"
               ::"r"(dst), "l"(m), "r"(bar), "r"(c0), "r"(c1), "r"(c2), "r"(c3) : "memory");
}
__device__ __forceinline__ void bulk_ld(uint32_t dst, const void* src, int bytes, uint32_t bar) {
  asm volatile("cp.async.bulk.shared::cluster.global.mbarrier::complete_tx::bytes [%0], [%1], %2, [%3];" ::"r"(dst), "l"(src), "r"(bytes), "r"(bar) : "memory");
}
__device__ __forceinline__ void bulk_ld_mc(uint32_t dst, const void* src, int bytes, uint32_t bar) {
  asm volatile("cp.async.bulk.shared::cluster.global.mbarrier::complete_tx::bytes.multicast::cluster [%0], [%1], %2, [%3], %4;"
               ::"r"(dst), "l"(src), "r"(bytes), "r"(bar), "h"((uint16_t)3) : "memory");
}
__device__ __forceinline__ void tma2d_st(const CUtensorMap* m, uint32_t src, int c0, int c1) {
  asm volatile("cp.async.bulk.tensor.2d.global.shared::cta.bulk_group [%0, {%2, %3}], [%1];" ::"l"(m), "r"(src), "r"(c0), "r"(c1) : "memory");
}
__device__ __forceinline__ void ldsm4(uint32_t (&r)[4], uint32_t a) {
  asm volatile("ldmatrix.sync.aligned.m8n8.x4.shared.b16 {%0,%1,%2,%3}, [%4];" : "=r"(r[0]), "=r"(r[1]), "=r"(r[2]), "=r"(r[3]) : "r"(a) : "memory");
}
__device__ __forceinline__ void ldsm4t(uint32_t (&r)[4], uint32_t a) {
  asm volatile("ldmatrix.sync.aligned.m8n8.x4.trans.shared.b16 {%0,%1,%2,%3}, [%4];" : "=r"(r[0]), "=r"(r[1]), "=r"(r[2]), "=r"(r[3]) : "r"(a) : "memory");
}
__device__ __forceinline__ void stsm4(uint32_t a, uint32_t r0, uint32_t r1, uint32_t r2, uint32_t r3) {
  asm volatile("stmatrix.sync.aligned.m8n8.x4.shared.b16 [%0], {%1,%2,%3,%4};" ::"r"(a), "r"(r0), "r"(r1), "r"(r2), "r"(r3) : "memory");
}
__device__ __forceinline__ uint32_t pk2(float lo, float hi) { uint32_t r; asm("cvt.rn.bf16x2.f32 %0, %1, %2;" : "=r"(r) : "f"(hi), "f"(lo)); return r; }
__device__ __forceinline__ uint32_t hmul(uint32_t a, uint32_t b) { uint32_t r; asm("mul.rn.bf16x2 %0, %1, %2;" : "=r"(r) : "r"(a), "r"(b)); return r; }
__device__ __forceinline__ uint32_t hadd(uint32_t a, uint32_t b) { uint32_t r; asm("add.rn.bf16x2 %0, %1, %2;" : "=r"(r) : "r"(a), "r"(b)); return r; }
__device__ __forceinline__ uint32_t hmaxabs(uint32_t a, uint32_t b) { uint32_t r; asm("max.xorsign.abs.bf16x2 %0, %1, %2;" : "=r"(r) : "r"(a), "r"(b)); return r; }
__device__ __forceinline__ float ex2(float x) { float r; asm("ex2.approx.ftz.f32 %0, %1;" : "=f"(r) : "f"(x)); return r; }
__device__ __forceinline__ float rcp_fast(float x) { float r; asm("rcp.approx.ftz.f32 %0, %1;" : "=f"(r) : "f"(x)); return r; }
__device__ __forceinline__ uint32_t phi2(float lo, float hi) {
  const float c = 1.4426950408889634f;
  uint32_t r;
  asm("max.bf16x2 %0, %1, %2;" : "=r"(r) : "r"(pk2(lo, hi)), "r"(hadd(pk2(ex2(-fabsf(fmaf(lo, c, -c))), ex2(-fabsf(fmaf(hi, c, -c)))), 0x35863586u)));
  return r;
}
__device__ __forceinline__ bool opaque_true() { uint32_t v; asm volatile("mov.u32 %0, %%nctaid.y;" : "=r"(v)); return v != 0; }
__device__ __forceinline__ int norm_exp(uint32_t (&v)[32], float f0) {
  uint32_t m[4] = {hmaxabs(__float_as_uint(f0) >> 16, v[0]), v[1], v[2], v[3]};
#pragma unroll
  for (int i = 4; i < 32; i++) m[i & 3] = hmaxabs(m[i & 3], v[i]);
  m[0] = hmaxabs(hmaxabs(m[0], m[1]), hmaxabs(m[2], m[3]));
  const int e = min(max((int)(__reduce_max_sync(~0u, max(m[0] & 0x7FFFu, (m[0] >> 16) & 0x7FFFu)) >> 7), 1), 253);
  if (e > 141) {
#pragma unroll
    for (int i = 0; i < 32; i++) v[i] = hmul(v[i], 0x07000700u);
  }
  return e;
}
__device__ __forceinline__ void norm_cvt(uint32_t (&v)[32], float f0, int e) {
  const uint32_t sc = (e > 141 ? 255 - e : 142 - e) * 0x00800080u;
#pragma unroll
  for (int i = 0; i < 32; i++) {
    const uint32_t a = hmul(v[i], sc);
    v[i] = (a & 0x0FFF0FFFu) * 7 + a;
  }
  v[0] = __byte_perm(v[0], __half_as_ushort(__float2half_rn(f0 * __uint_as_float((254 - e) << 23))), 0x3254);
}
__device__ __forceinline__ void poll_ge(const unsigned* p, unsigned target) {
#pragma unroll 1
  for (int n = 0; n < SPIN_LIMIT; n++) {
    unsigned v;
    asm volatile("ld.relaxed.gpu.global.u32 %0, [%1];" : "=r"(v) : "l"(p) : "memory");
    if (__all_sync(~0u, (int)(v - target) >= 0)) { asm volatile("fence.acquire.gpu;" ::: "memory"); return; }
  }
  __trap();
}

__device__ __forceinline__ bool elect_one() {
  uint32_t p;
  asm volatile("{\n.reg .pred p;\nelect.sync _|p, 0xffffffff;\nselp.u32 %0, 1, 0, p;\n}\n" : "=r"(p));
  return p;
}
__device__ __forceinline__ uint4 ld_na4(const void* p) {
  uint4 v;
  asm volatile("ld.global.L1::no_allocate.v4.u32 {%0,%1,%2,%3}, [%4];" : "=r"(v.x), "=r"(v.y), "=r"(v.z), "=r"(v.w) : "l"(p) : "memory");
  return v;
}
__device__ __forceinline__ void st_cg4(void* p, uint4 v) {
  asm volatile("st.global.cg.v4.u32 [%0], {%1,%2,%3,%4};" ::"l"(p), "r"(v.x), "r"(v.y), "r"(v.z), "r"(v.w) : "memory");
}
__device__ __forceinline__ uint32_t mapa(uint32_t a, uint32_t cta) { uint32_t r; asm("mapa.shared::cluster.u32 %0, %1, %2;" : "=r"(r) : "r"(a), "r"(cta)); return r; }
__device__ __forceinline__ void st_async(uint32_t a, uint32_t v, uint32_t bar) {
  asm volatile("st.async.weak.shared::cluster.mbarrier::complete_tx::bytes.b32 [%0], %1, [%2];" ::"r"(a), "r"(v), "r"(bar) : "memory");
}
__device__ __forceinline__ void st_async4(uint32_t a, uint32_t x, uint32_t y, uint32_t z, uint32_t w, uint32_t bar) {
  asm volatile("st.async.weak.shared::cluster.mbarrier::complete_tx::bytes.v4.b32 [%0], {%1,%2,%3,%4}, [%5];" ::"r"(a), "r"(x), "r"(y), "r"(z), "r"(w), "r"(bar) : "memory");
}
__device__ __forceinline__ void tma_q_ld(uint32_t dst, const CUtensorMap* m, int ch, int quarter, int g0, uint32_t bar) {
  asm volatile("cp.async.bulk.tensor.5d.shared::cluster.global.mbarrier::complete_tx::bytes [%0], [%1, {%3, %6, %6, %4, %5}], [%2];"
               ::"r"(dst), "l"(m), "r"(bar), "r"(ch), "r"(8 * quarter), "r"(g0), "r"(0) : "memory");
}
__device__ __forceinline__ void tma_q_st(const CUtensorMap* m, uint32_t src, int ch, int quarter, int g0) {
  asm volatile("cp.async.bulk.tensor.5d.global.shared::cta.bulk_group [%0, {%2, %5, %5, %3, %4}], [%1];"
               ::"l"(m), "r"(src), "r"(ch), "r"(8 * quarter), "r"(g0), "r"(0) : "memory");
}
__device__ __forceinline__ uint4 ld_rlx4(const void* p) {
  uint4 v;
  asm volatile("{\n.reg .b128 t;\n.reg .b64 a, b;\nld.relaxed.gpu.global.b128 t, [%4];\nmov.b128 {a, b}, t;\nmov.b64 {%0, %1}, a;\nmov.b64 {%2, %3}, b;\n}\n"
               : "=r"(v.x), "=r"(v.y), "=r"(v.z), "=r"(v.w) : "l"(p) : "memory");
  return v;
}
__device__ __forceinline__ void ld_stale4(uint4& v, const void* p, uint32_t tag) {
  asm volatile("{\n.reg .b128 t;\n.reg .b64 a, b;\n.reg .b32 x;\n.reg .pred p;\n"
               "lop3.b32 x, %0, %5, 1, 0x28;\nsetp.ne.u32 p, x, 0;\n"
               "mov.b64 a, {%0, %1};\nmov.b64 b, {%2, %3};\nmov.b128 t, {a, b};\n"
               "@p ld.relaxed.gpu.global.b128 t, [%4];\n"
               "mov.b128 {a, b}, t;\nmov.b64 {%0, %1}, a;\nmov.b64 {%2, %3}, b;\n}\n"
               : "+r"(v.x), "+r"(v.y), "+r"(v.z), "+r"(v.w) : "l"(p), "r"(tag) : "memory");
}
__device__ __forceinline__ void st_tag4(void* p, float a, float b, float c, float d, uint32_t tag) {
  asm volatile("{\n.reg .b128 t;\n.reg .b64 a, b;\nmov.b64 a, {%1, %2};\nmov.b64 b, {%3, %4};\nmov.b128 t, {a, b};\nst.relaxed.gpu.global.b128 [%0], t;\n}\n"
               ::"l"(p), "r"((__float_as_uint(a) & ~1u) | tag), "f"(b), "f"(c), "f"(d) : "memory");
}
__device__ __forceinline__ uint32_t stale8(const uint4 (&f)[8], uint32_t tag) {
  uint32_t r[4];
#pragma unroll
  for (int i = 0; i < 4; i++) asm("lop3.b32 %0, %1, %2, %3, 0x7E;" : "=r"(r[i]) : "r"(f[2 * i].x), "r"(f[2 * i + 1].x), "r"(tag));
  asm("lop3.b32 %0, %0, %1, %2, 0xFE;" : "+r"(r[0]) : "r"(r[1]), "r"(r[2]));
  return r[0] | r[3];
}

struct ConvC { uint32_t a1[2][4], wa[2], wb[2], sg; };
__device__ __forceinline__ uint64_t dsc(uint32_t lo, uint32_t hi) { return ((uint64_t)hi << 32) | lo; }
__device__ __forceinline__ uint32_t hfma(uint32_t a, uint32_t b, uint32_t c) { uint32_t r; asm("fma.rn.f16x2 %0, %1, %2, %3;" : "=r"(r) : "r"(a), "r"(b), "r"(c)); return r; }
__device__ __forceinline__ uint32_t hfnma(uint32_t a, uint32_t b, uint32_t c) { uint32_t r; asm("{.reg .b32 n; neg.f16x2 n, %1; fma.rn.f16x2 %0, n, %2, %3;}" : "=r"(r) : "r"(a), "r"(b), "r"(c)); return r; }
__device__ __forceinline__ uint32_t hmul16(uint32_t a, uint32_t b) { uint32_t r; asm("mul.rn.f16x2 %0, %1, %2;" : "=r"(r) : "r"(a), "r"(b)); return r; }
template <int N> __device__ __forceinline__ void keepu(uint32_t (&d)[N]) {
#pragma unroll
  for (int i = 0; i < N; i++) asm volatile("" : "+r"(d[i])::"memory");
}
__device__ __forceinline__ void conv_m1(const ConvC& K, uint32_t (&u)[16], uint32_t l) {
  wg_fence();
  wgmma_hrs_n64<1>(u, K.a1[0][0], K.a1[0][1], K.a1[0][2], K.a1[0][3], dsc(l, 32), 0);
  wgmma_hrs_n64<1>(u, K.a1[1][0], K.a1[1][1], K.a1[1][2], K.a1[1][3], dsc(l + 16, 32), 1);
  wg_commit();
}
__device__ __forceinline__ void conv_s2(const ConvC& K, uint32_t (&u)[16], uint32_t (&Z)[2][8], uint32_t dfl) {
  uint32_t fr[8], fi[8];
#pragma unroll
  for (int c = 0; c < 8; c++) {
    const uint32_t r = hfma(K.wa[c & 1], u[2 * c + 1], u[2 * c]);
    fi[c] = hfma(K.wb[c & 1], r, u[2 * c + 1]);
    fr[c] = hfma(K.wa[c & 1], fi[c], r);
  }
  wg_fence();
#pragma unroll
  for (int p = 0; p < 2; p++) {
    wgmma_hrs_n32<0>(Z[p], fr[4 * p], fr[4 * p + 2], fr[4 * p + 1], fr[4 * p + 3], dsc(dfl, 32), 0);
    wgmma_hrs_n32<0>(Z[p], fi[4 * p], fi[4 * p + 2], fi[4 * p + 1], fi[4 * p + 3], dsc(dfl + 16, 32), 1);
  }
  wg_commit();
}
__device__ __forceinline__ void conv_win(const ConvC& K, const uint32_t (&X)[2][8], uint32_t (&W)[2][8]) {
#pragma unroll
  for (int b = 0; b < 4; b++)
#pragma unroll
    for (int c = 0; c < 2; c++) {
      const uint32_t xr = X[b >> 1][2 * c + (b & 1)], xi = X[b >> 1][4 + 2 * c + (b & 1)];
      const int a = b ? b - 1 : 0;
      W[b >> 1][2 * c + (b & 1)] = b ? hfnma(K.sg, X[a >> 1][4 + 2 * c + (a & 1)], xr) : xr;
      W[b >> 1][4 + 2 * c + (b & 1)] = b ? hfma(K.sg, X[a >> 1][2 * c + (a & 1)], xi) : xi;
    }
}
template <int p>
__device__ __forceinline__ void conv_pw(uint32_t (&X)[2][8], uint32_t (&H)[2][8], uint32_t (&V)[8], uint32_t dil) {
  uint32_t pr[2][2], pi[2][2];
#pragma unroll
  for (int jj = 0; jj < 2; jj++)
#pragma unroll
    for (int c = 0; c < 2; c++) {
      const int j = 2 * p + jj;
      uint32_t sr = 0, si = 0;
#pragma unroll
      for (int a = 0; a <= j; a++) {
        const int b = j - a;
        const uint32_t hr = H[a >> 1][2 * c + (a & 1)], hi = H[a >> 1][4 + 2 * c + (a & 1)];
        const uint32_t xr = X[b >> 1][2 * c + (b & 1)], xi = X[b >> 1][4 + 2 * c + (b & 1)];
        sr = a == 0 ? hmul16(hr, xr) : hfma(hr, xr, sr);
        si = a == 0 ? hmul16(hr, xi) : hfma(hr, xi, si);
        sr = hfnma(hi, xi, sr);
        si = hfma(hi, xr, si);
      }
      pr[jj][c] = sr; pi[jj][c] = si;
    }
  wg_fence();
  wgmma_hrs_n32<0>(V, pr[0][0], pr[1][0], pr[0][1], pr[1][1], dsc(dil, 32), 0);
  wgmma_hrs_n32<0>(V, pi[0][0], pi[1][0], pi[0][1], pi[1][1], dsc(dil + 16, 32), 1);
  wg_commit();
}
template <int p>
__device__ __forceinline__ void conv_it(const ConvC& K, uint32_t (&V)[8], uint32_t vst) {
#pragma unroll
  for (int jj = 0; jj < 2; jj++) {
    uint32_t wr[2], wi[2];
#pragma unroll
    for (int c = 0; c < 2; c++) {
      const uint32_t r = hfnma(K.wa[c], V[4 + 2 * c + jj], V[2 * c + jj]);
      wi[c] = hfnma(K.wb[c], r, V[4 + 2 * c + jj]);
      wr[c] = hfnma(K.wa[c], wi[c], r);
    }
    stsm4(vst + (2 * p + jj) * 2048, wr[0], wr[1], wi[0], wi[1]);
  }
}
__device__ __forceinline__ void conv_m4(uint32_t (&y)[8], uint32_t (&a)[4][4], uint32_t d4l) {
  wg_fence();
  wgmma_hrs_n32<0>(y, a[0][0], a[0][1], a[0][2], a[0][3], dsc(d4l, 64), 0);
#pragma unroll
  for (int s = 1; s < 4; s++) wgmma_hrs_n32<0>(y, a[s][0], a[s][1], a[s][2], a[s][3], dsc(d4l + s * 16, 64), 1);
  wg_commit();
}

struct Params {
  CUtensorMap tmX0, tmW, tmX, tmWo, tmWo1, tmK, tmV, tmQ, tmOA, tmOB;
  const __nv_bfloat16 *shift_k, *h, *D, *x, *w, *wo, *q;
  float *part, *kv;
  uint4* o;
  const uint32_t *thr, *img;
};

__global__ void __cluster_dims__(2, 1, 1) __launch_bounds__(384, 1) fused_kernel(const __grid_constant__ Params P) {
  extern __shared__ __align__(1024) uint8_t smem[];
#define MAP_PF(m) asm volatile("prefetch.tensormap [%0];" ::"l"(&P.m) : "memory")
  if (threadIdx.x == 0) { MAP_PF(tmX0); MAP_PF(tmW); MAP_PF(tmX); }
  const uint32_t sb = __shfl_sync(~0u, smem_u32(smem), 0);
  const uint32_t bars = sb + OFF_BAR;
  const int tid = threadIdx.x, lane = tid & 31;
  const int warp = __shfl_sync(~0u, tid >> 5, 0);
  const int rank = blockIdx.x & 1, pc = blockIdx.x >> 1;
  const unsigned c7 = pc + 6, g7 = (c7 * 37) >> 8;
  const int mb = pc < 4 ? 4 + pc : pc < 36 ? (pc - 4) >> 3 : g7 - 2;
  const int hq = pc < 4 ? 0 : pc < 36 ? (pc - 4) & 7 : 1 + c7 - 7 * g7;
  const int cl = 8 * hq + mb;
  const int hp = 2 * hq + rank;
  const int rb = 2 * mb + (hq >> 2), cb = hq & 3;
#define BAR(i) (bars + 8 * (i))
#define OCNT(rb, hh) ((unsigned*)(P.o + (rb) * OBLK + 16 * 1024 + 8 * (hh)))
#define EPOCH (OCNT(rb, 2)[hp & 7])

  if (tid == 0) { STAMP(0, 0); GSTAMP(0, 30); }
  if (warp == 8) {
    if (elect_one()) {
      mbar_init(BAR(B_FIRST), 1);
      asm volatile("fence.mbarrier_init.release.cluster;" ::: "memory");
      mbar_expect(BAR(B_FIRST), STAGE_BYTES - 16384);
      tma2d(sb, &P.tmX0, 0, mb * 256, BAR(B_FIRST));
      tma2d(sb + 16384, &P.tmX0, 0, mb * 256 + 128, BAR(B_FIRST));
      tma3d(sb + 32768, &P.tmW, hp * 64, 0, 0, BAR(B_FIRST));
      mbar_init(BAR(B_FULL1), 1);
      asm volatile("fence.mbarrier_init.release.cluster;" ::: "memory");
    }
    if (lane == 0) STAMP(3, 21);
  } else if (lane == 0) {
    const int wi = warp - (warp > 8);
#pragma unroll
    for (int r = 0; r < 6; r++)
      if (r < 5 || wi < B_COUNT - 56) mbar_init(BAR(1 + 11 * r + wi), ((uint32_t)(bar_counts(r) >> (4 * wi)) & 15) + 1);
    asm volatile("fence.mbarrier_init.release.cluster;" ::: "memory");
  }
  if (tid == 0) STAMP(2, 6);
  asm volatile("barrier.cluster.arrive.relaxed.aligned;\nbarrier.cluster.wait.aligned;" ::: "memory");
  if (warp == 8 && elect_one()) {
    mbar_expect(BAR(B_FULL1), 16384);
    tma2d_mc(sb + 8192 + rank * 16384, &P.tmX0, 0, mb * 256 + 64 + rank * 128, BAR(B_FULL1));
  }
  if (tid == 256) STAMP(2, 7);

  if (warp < 8) {
    asm volatile("setmaxnreg.inc.sync.aligned.u32 224;");
    const int wg = warp >> 2, w = warp & 3, g = lane >> 2, q = lane & 3, t = tid & 127;
    const bool elect = (t == 0);
    const uint32_t s16 = (sb & 0x3FFFF) >> 4;
    uint32_t pq[2][16], ux[16], uh[16], X[4][2][8], H[4][2][8];
    ConvC K;
    const uint32_t dfl = s16 + (OFF_F2F >> 4) + (8 << 16), dil = s16 + (OFF_F2I >> 4) + (8 << 16), d4l = s16 + (OFF_F4 >> 4) + (8 << 16);
    const uint32_t xl = s16 + (OFF_XT >> 4) + 4 * wg * (XT_STRIDE >> 4) + (8 << 16);
    const uint32_t hl = s16 + (OFF_H >> 4) + wg * 512 + (8 << 16);
    {
      float acc[2][96];
      {
#pragma unroll
        for (int i = 0; i < 192; i++) { acc[i / 96][i % 96] = i % 96 < 64 ? 1.f : 0.f; asm volatile("" : "+f"(acc[i / 96][i % 96])); }
      }
      {
#pragma unroll
        for (int mt = 0; mt < 2; mt++) {
          mbar_wait(BAR(mt ? B_FULL1 : B_FIRST), 0);
          if (mt == 0 && elect) { STAMP(wg, 1); GSTAMP(wg, 26); }
          wg_fence();
#pragma unroll
          for (int ks = 0; ks < 4; ks++)
            wgmma_ss_n192<0, 1>(acc[mt], dsc(s16 + wg * 1024 + mt * 512 + (1 << 16) + ks * 2, SW128), dsc(s16 + 2048 + (512 << 16) + ks * 128, SW128), 1);
        }
        wg_commit();
      }
      int st = 1, ph = 0;
#pragma unroll 1
      for (int kb = 1; kb < 14; kb++) {
        mbar_wait(BAR(B_FULL1 + st), ph);
        if (kb == 8 && elect) { STAMP(wg, 16); GSTAMP(wg, 25); }
        const uint32_t da = s16 + st * (STAGE_BYTES >> 4) + wg * 1024 + (1 << 16);
        const uint32_t db = s16 + st * (STAGE_BYTES >> 4) + 2048 + (512 << 16);
        wg_fence();
#pragma unroll
        for (int ks = 0; ks < 4; ks++) {
          wgmma_ss_n192<0, 1>(acc[0], dsc(da + ks * 2, SW128), dsc(db + ks * 128, SW128), 1);
          wgmma_ss_n192<0, 1>(acc[1], dsc(da + 512 + ks * 2, SW128), dsc(db + ks * 128, SW128), 1);
        }
        wg_commit();
        wg_wait<1>();
        if (t < 2) mbar_arrive_cl(BAR(B_EMPTY1 + (st == 0 ? 2 : st - 1)), t);
        if (++st == 3) { st = 0; ph ^= 1; }
      }
#define TAIL_MMA(mt, stage) do { wg_fence(); _Pragma("unroll") for (int ks = 0; ks < 4; ks++) \
        wgmma_ss_n192<0, 1>(acc[mt], dsc(s16 + (stage) * (STAGE_BYTES >> 4) + wg * 1024 + (mt) * 512 + (1 << 16) + ks * 2, SW128), \
                            dsc(s16 + (stage) * (STAGE_BYTES >> 4) + 2048 + (512 << 16) + ks * 128, SW128), 1); wg_commit(); } while (0)
      mbar_wait(BAR(B_FULL1 + 2), 0);
      TAIL_MMA(0, 2);
      wg_wait<1>();
      if (elect) mbar_arrive(BAR(B_SFREE));
      mbar_wait(BAR(B_FULL1 + 0), 1);
      TAIL_MMA(0, 0);
      TAIL_MMA(1, 2);
      const uint32_t lrow = sb + wg * 16384 + (16 * w + 8 * ((lane >> 3) & 1) + (lane & 7)) * 128 + (((lane >> 4) ^ (lane & 7)) << 4);
#define E1K(mt, i) do { if (opaque_true()) { _Pragma("unroll") for (int j = (i); j < (i) + 2; j++) { \
          const float* a = &acc[mt][32 + 8 * j]; const float* b = a + 32; const uint32_t o = (lrow ^ (j * 32)) + (mt) * 8192; \
          stsm4(o + 2 * STAGE_BYTES, pk2(b[0], b[1]), pk2(b[2], b[3]), pk2(b[4], b[5]), pk2(b[6], b[7])); \
          stsm4(o, phi2(a[0], a[1]), phi2(a[2], a[3]), phi2(a[4], a[5]), phi2(a[6], a[7])); } } } while (0)
#define E1Q(mt) do { if (opaque_true()) { _Pragma("unroll") for (int i = 0; i < 16; i++) pq[mt][i] = phi2(acc[mt][2 * i], acc[mt][2 * i + 1]); } } while (0)
#define LOAD_K() do { const uint4* ct = (const uint4*)P.thr + t; \
        _Pragma("unroll") for (int s = 0; s < 2; s++) { const uint4 u = ld_na4(ct + s * 128); K.a1[s][0] = u.x; K.a1[s][1] = u.y; K.a1[s][2] = u.z; K.a1[s][3] = u.w; } \
        const uint4 u = ld_na4(ct + 2 * 128); K.wa[0] = u.x; K.wa[1] = u.y; K.wb[0] = u.z; K.wb[1] = u.w; \
        K.sg = (lane & 4) ? 0xBC00BC00u : 0x3C003C00u; } while (0)
#define PK_READY(mt) do { fence_async(); __syncwarp(); if (lane == 0) mbar_arrive(BAR(B_PKRDY + (mt))); } while (0)
      wg_wait<1>();
      keep(acc[0]);
      if (elect) STAMP(wg, 18);
      E1K(0, 0);
      TAIL_MMA(1, 0);
      E1K(0, 2);
      if (elect) STAMP(wg, 19);
      PK_READY(0);
      wg_wait<0>();
      keep(acc[1]);
      if (elect) mbar_arrive(BAR(B_G1DONE));
      asm volatile("setmaxnreg.dec.sync.aligned.u32 %0;" ::"n"(RC));
      if (elect) { STAMP(wg, 2); GSTAMP(wg, 27); }
      E1K(1, 0);
      if (elect) STAMP(wg, 20);
      E1K(1, 2);
      if (elect) STAMP(wg, 21);
      PK_READY(1);
      if (elect) STAMP(wg, 3);
      LOAD_K();
      if (elect) STAMP(wg, 4);
      E1Q(0);
      E1Q(1);
      if (elect) STAMP(wg, 17);
      mbar_wait(BAR(B_H), 0);
      conv_m1(K, ux, xl);
      conv_m1(K, uh, hl);
      wg_wait<1>(); keepu(ux);
      if (lane == 0) mbar_arrive_cl(BAR(B_XFREE + 4 * wg), rank ^ 1);
      conv_s2(K, ux, X[0], dfl);
      wg_wait<1>(); keepu(uh);
      conv_s2(K, uh, H[0], dfl);
    }
    if (elect) STAMP(wg, 5);
    float acc[64];
#define G2_MMA(da, db, first) do { wg_fence(); _Pragma("unroll") for (int ks = 0; ks < 4; ks++) \
        wgmma_ss_n128<0, 1>(acc, dsc((da) + ks * 2, SW128), dsc((db) + ks * 128, SW128), ks || !(first)); wg_commit(); } while (0)
    const uint32_t a0 = s16 + wg * 512 + (1 << 16), b0 = s16 + (512 << 16);
    uint32_t cons = mapa(BAR(B_CONS2 - 1 + G2E), t & 1);
    const bool rel = __shfl_sync(~0u, t, lane) < 2;
    {
      uint32_t vst = sb + wg * 8192 + w * 512 + lane * 16, vld = sb + wg * 8192 + w * 2048 + lane * 16;
      uint32_t ya = mapa(sb + OFF_XT + 4 * wg * XT_STRIDE + (2 * rank + (w & 1)) * 1024 + lane * 16, w >> 1);
      const uint32_t ybar = mapa(BAR(B_Y), w >> 1);
      asm volatile("" : "+r"(vst), "+r"(vld), "+r"(ya));
      uint32_t W[2][8], V0[8], V1[8], y[8], a[4][4];
      uint4 ov[4];
      uint4* const ot = P.o + (2 * mb + wg) * OBLK + hq * 1024 + (16 * w + g) * 8 + ((4 * rank + q) ^ g);
#define YOUT(i) do { if ((w >> 1) == rank) { \
          asm volatile("st.shared.v4.b32 [%0], {%1,%2,%3,%4};" ::"r"(ya + (i) * XT_STRIDE), "r"(y[0]), "r"(y[1]), "r"(y[2]), "r"(y[3]) : "memory"); \
          asm volatile("st.shared.v4.b32 [%0], {%1,%2,%3,%4};" ::"r"(ya + (i) * XT_STRIDE + 512), "r"(y[4]), "r"(y[5]), "r"(y[6]), "r"(y[7]) : "memory"); \
        } else { \
          mbar_wait(BAR(B_XFREE + 4 * wg + (i)), 0); \
          st_async4(ya + (i) * XT_STRIDE, y[0], y[1], y[2], y[3], ybar); \
          st_async4(ya + (i) * XT_STRIDE + 512, y[4], y[5], y[6], y[7], ybar); } } while (0)
      auto ocalc = [&](const int hh) {
        if (hh == 0) {
          if (elect) STAMP(wg, 8);
          mbar_wait(BAR(B_KV), 0);
          if (elect) STAMP(wg, 9);
        } else mbar_wait(BAR(B_KV1), 0);
        float oa[2][20];
        wg_fence();
#pragma unroll
        for (int m = 0; m < 4; m++) {
          const uint32_t* p = &pq[m & 1][8 * hh + 4 * (m >> 1)];
          wgmma_rs_n40<1>(oa[m & 1], p[0], p[1], p[2], p[3], dsc(s16 + (OFF_KVB >> 4) + hh * 160 + (m >> 1) * 16 + (8 << 16), 32), m >> 1);
        }
        wg_commit();
        wg_wait<0>();
#pragma unroll
        for (int mt = 0; mt < 2; mt++) {
          float (&o)[20] = oa[mt];
          keep(o);
          const uint32_t den = hadd(pk2(o[16], o[18]), 0x35863586u);
#pragma unroll
          for (int r = 0; r < 2; r++) {
            const float ri = rcp_fast(__uint_as_float(r ? (den & 0xFFFF0000u) : (den << 16)));
            uint4 u;
            u.x = pk2(o[2 * r] * ri, o[2 * r + 1] * ri);
            u.y = pk2(o[4 + 2 * r] * ri, o[5 + 2 * r] * ri);
            u.z = pk2(o[8 + 2 * r] * ri, o[9 + 2 * r] * ri);
            u.w = pk2(o[12 + 2 * r] * ri, o[13 + 2 * r] * ri);
            if (hh == 0) st_cg4(ot + (64 * mt + 8 * r) * 8, u); else ov[2 * mt + r] = u;
          }
        }
        if (hh == 0) {
          __syncwarp();
          if (lane == 0) mbar_arrive(BAR(B_ODONE));
          if (elect) STAMP(wg, 10);
        }
      };
      auto trickle = [&](const int qs) {
        const int m = qs - 2 * (OCH + O1D) - (TRICK - 1);
        if (m >= 0 && m < 4) {
          st_cg4(ot + 8 * 1024 + (64 * (m >> 1) + 8 * (m & 1)) * 8, ov[m]);
          if (m == 3) { __syncwarp(); if (lane == 0) mbar_arrive(BAR(B_ODONE1)); }
        }
      };
#pragma unroll
      for (int i = 0; i < 4; i++) {
        const bool nx = i < 3;
        const int n = nx ? i + 1 : i;
        const uint32_t vo = (i & 1) ? OFF_H + (i >> 1) * 16384 : OFF_VP;
        if (2 * i == OCH) ocalc(0);
        if (2 * i == OCH + O1D) ocalc(1);
        if (nx) {
          conv_m1(K, ux, xl + n * (XT_STRIDE >> 4));
          conv_m1(K, uh, hl + (n >> 1) * 1024 + (n & 1) * 256);
        }
        if (2 * i != OCH && 2 * i != OCH + O1D) { if (nx) { if (i > 0) wg_wait<3>(); else wg_wait<2>(); } else wg_wait<1>(); }
        keepu(X[i][0]); keepu(X[i][1]); keepu(H[i][0]); keepu(H[i][1]);
        conv_win(K, X[i], W);
        trickle(4 * i);
        conv_pw<0>(W, H[i], V0, dil);
        conv_pw<1>(W, H[i], V1, dil);
        trickle(4 * i + 1);
        wg_wait<2>();
        if (i > 0) { keepu(y); YOUT(i - 1); }
        if (2 * i + 1 == OCH) ocalc(0);
        if (2 * i + 1 == OCH + O1D) ocalc(1);
        if (nx) {
          keepu(ux); keepu(uh);
          if (lane == 0) mbar_arrive_cl(BAR(B_XFREE + 4 * wg + n), rank ^ 1);
          conv_s2(K, ux, X[n], dfl);
          wg_wait<1>();
        } else wg_wait<0>();
        keepu(V0); keepu(V1);
        if (G2E && G2P == 0 && i == 3) { mbar_wait(BAR(B_FULL2), 0); G2_MMA(a0 + (SLOT_A & 15) * 1024, b0 + (SLOT_B & 15) * 1024, true); }
        trickle(4 * i + 2);
        if (i == 0) mbar_wait(BAR(B_H2), 0);
        conv_it<0>(K, V0, vst + vo);
        conv_it<1>(K, V1, vst + vo);
        if (G2E && G2P == 1 && i == 3) { mbar_wait(BAR(B_FULL2), 0); G2_MMA(a0 + (SLOT_A & 15) * 1024, b0 + (SLOT_B & 15) * 1024, true); }
        bar_sync(1 + wg);
#pragma unroll
        for (int s = 0; s < 4; s++) ldsm4t(a[s], vld + vo + s * 512);
        if (nx) conv_s2(K, uh, H[n], dfl);
        conv_m4(y, a, d4l);
        trickle(4 * i + 3);
        if (i > 0 && lane < 2) mbar_arrive_cl(BAR(B_AFREE + i - 1), lane);
        if (elect && i < 3) STAMP(wg, i < 2 ? 6 + i : 9 + i);
      }
      if (G2E && G2P == 2) { mbar_wait(BAR(B_FULL2), 0); G2_MMA(a0 + (SLOT_A & 15) * 1024, b0 + (SLOT_B & 15) * 1024, true); wg_wait<1>(); }
      else wg_wait<0>();
      keepu(y);
      if (G2E && G2P < 2 && rel) asm volatile("mbarrier.arrive.shared::cluster.b64 _, [%0];" ::"r"(cons) : "memory");
      YOUT(3);
      __syncwarp();
      if (lane == 0) mbar_arrive(BAR(B_Y));
      if (elect) STAMP(wg, 12);
    }
    {
      uint64_t ta = SLOT_A >> (4 * G2E), tb = SLOT_B >> (4 * G2E);
      uint32_t da = a0 + ((uint32_t)ta & 15) * 1024, db = b0 + ((uint32_t)tb & 15) * 1024, fb = BAR(B_FULL2 + G2E);
#pragma unroll 1
      for (int kb = G2E; kb < HOLD2; kb++) {
        mbar_wait(fb, 0);
        G2_MMA(da, db, kb == 0);
        ta >>= 4; tb >>= 4;
        da = a0 + ((uint32_t)ta & 15) * 1024; db = b0 + ((uint32_t)tb & 15) * 1024; fb += 8;
        asm volatile("" : "+r"(da), "+r"(db));
        wg_wait<1>();
        if ((kb > G2E || (G2E && G2P == 2)) && kb < 12 && rel) asm volatile("mbarrier.arrive.shared::cluster.b64 _, [%0];" ::"r"(cons) : "memory");
        cons += 8;
      }
#pragma unroll
      for (int kb = HOLD2; kb < 16; kb++) {
        if (wg == 1) mbar_wait(BAR(B_FULL2 + kb), 0);
        else if (kb == HOLD2) asm volatile("bar.sync 3, 256;" ::: "memory");
        G2_MMA(a0 + ((SLOT_A >> (4 * kb)) & 15) * 1024, b0 + ((SLOT_B >> (4 * kb)) & 15) * 1024, false);
      }
      if (wg == 1) asm volatile("bar.arrive 3, 256;" ::: "memory");
      const uint32_t stg = sb + wg * 8192 + w * 2048, so0 = ((SLOT_A >> 56) & 15) * 16384, so1 = ((SLOT_A >> 60) & 15) * 16384;
      const uint32_t lrow = stg + (8 * ((lane >> 3) & 1) + (lane & 7)) * 128 + (((lane >> 4) ^ (lane & 7)) << 4);
      const int col = 1024 + 256 * cb + 128 * rank, row = 128 * rb + 64 * wg + 16 * w;
      wg_wait<0>();
      keep(acc);
      if (elect) { STAMP(wg, 14); GSTAMP(wg, 29); }
#pragma unroll
      for (int cp = 0; cp < 8; cp++) {
        const float* a = &acc[8 * cp];
        stsm4((lrow ^ ((cp & 3) * 32)) + (cp >> 2 ? so1 : so0), pk2(a[0], a[1]), pk2(a[2], a[3]), pk2(a[4], a[5]), pk2(a[6], a[7]));
        if ((cp & 3) == 3) {
          fence_async();
          __syncwarp();
          if (elect_one()) tma2d_st(&P.tmOB, stg + (cp >> 2 ? so1 : so0), col + (cp >> 2) * 64, row);
        }
      }
      asm volatile("cp.async.bulk.commit_group;\ncp.async.bulk.wait_group.read 0;" ::: "memory");
      if (elect) {
        STAMP(wg, 15); GSTAMP(wg, 31); PDUMP(wg); if (wg == 0) PDUMP(2);
      }
    }
  } else {
    asm volatile("setmaxnreg.dec.sync.aligned.u32 56;");
    const int hw = warp - 9, g = lane >> 2, q = lane & 3;
#define sbar (bars + 8 * (B_STG - 18) + 16 * warp)
    if (warp == 8) {
      if (D1) __nanosleep(D1);
      int st = 1, pp = 1;
      const uint8_t* pfx = (const uint8_t*)P.x + (mb * 256 + hp * 16 + (lane & 15)) * 2048;
      const uint8_t* pfw = (const uint8_t*)P.w + (mb * 8 + (lane & 7)) * 6144 + (lane >> 3) * 2048 + hp * 128;
#pragma unroll 1
      for (int kb = 1; kb < 16; kb++) {
        if (kb >= 3) mbar_wait(BAR(B_EMPTY1 + st), pp);
        const uint32_t sa = sb + st * STAGE_BYTES;
        if (elect_one()) {
          mbar_expect(BAR(B_FULL1 + st), STAGE_BYTES);
          tma2d_mc(sa + rank * 16384, &P.tmX, kb * 64, mb * 256 + rank * 128, BAR(B_FULL1 + st));
          tma3d(sa + 32768, &P.tmW, hp * 64, kb * 64, 0, BAR(B_FULL1 + st));
        }
        if (kb == 1 && lane == 0) STAMP(2, 24);
        if (PFD && kb >= 2) {
#pragma unroll 1
          for (int j = kb == 2 ? 3 : kb + PFD; j <= kb + PFD && j < 16; j++) {
            if (lane < 16) asm volatile("prefetch.global.L2 [%0];" ::"l"(pfx + j * 128));
            if (lane < 24) asm volatile("prefetch.global.L2 [%0];" ::"l"(pfw + j * (64 * 6144)));
          }
          if (kb >= QPF && kb < QPF + 8) asm volatile("prefetch.global.L2 [%0];" ::"l"((const uint8_t*)P.q + (blockIdx.x * 256 + (kb - QPF) * 16 + (lane & 16) * 8 + (lane & 15)) * 128));
          if (kb >= 4)
            asm volatile("prefetch.global.L2 [%0];" ::"l"(kb < 12 ? (const uint8_t*)P.h + ((2 * cl + rank) * 256 + (kb - 4) * 32 + lane) * 128
                                                                  : (const uint8_t*)P.wo + (blockIdx.x * 128 + (kb - 12) * 32 + lane) * 128));
        }
        if (++st == 3) { st = 0; pp ^= 1; }
      }
      if (elect_one()) { MAP_PF(tmWo); MAP_PF(tmWo1); }
      if (lane == 0) STAMP(2, 1);
    } else {
      {
        const uint32_t clk0 = __shfl_sync(~0u, (uint32_t)clock(), 0), stg = sb + OFF_STG + hw * STG_STRIDE;
        const unsigned epoch = __shfl_sync(~0u, EPOCH, 0);
        const uint32_t tag = ~epoch & 1;
        uint32_t tap[2][4];
#pragma unroll
        for (int cg = 0; cg < 2; cg++) {
          const uint2 u = __ldg((const uint2*)(P.shift_k + (16 * cl + 8 * cg + g) * 4));
          tap[cg][0] = __byte_perm(u.x, 0, 0x1010); tap[cg][1] = __byte_perm(u.x, 0, 0x3232);
          tap[cg][2] = __byte_perm(u.y, 0, 0x1010); tap[cg][3] = __byte_perm(u.y, 0, 0x3232);
        }
        if (hw == 0 && lane < 8) *(float*)(smem + OFF_D + 4 * lane) = __bfloat162float(P.D[16 * cl + 8 * rank + lane]);
        if (hw == 1 && lane < 24) asm volatile("prefetch.global.L2 [%0];" ::"l"(P.thr + (lane + 24 * rank) * 32));
        if (hw == 0 && elect_one()) {
          *(volatile unsigned*)(smem + OFF_EPOCH) = epoch;
          mbar_expect(BAR(B_XRAW), 16384);
          mbar_expect(BAR(B_Y), 16384 + 64);
        }
#pragma unroll 1
        for (int i = hw * 32 + lane; i < 528; i += 96) st_tag4(P.part + (hp * 8 + mb) * 2176 + 4 * i, 0.f, 0.f, 0.f, 0.f, tag ^ 1);
        if (hw < 2 || lane < 2) st_tag4(P.kv + hp * 2176 + (4 * (hw < 2 ? 64 * mb + 32 * hw + lane : 512 + 8 * (mb & 1) + (mb & 6) + lane)), 0.f, 0.f, 0.f, 0.f, tag ^ 1);
        if (lane == 0) STAMP(3, hw);
        const uint32_t xo = sb + OFF_XT + g * XT_STRIDE + rank * 2048 + q * 4;
        const int krow = 8 + (lane & 7) - (lane >> 3);
        const uint32_t ka = stg + krow * 32 + ((krow & 4) << 2), va = stg + 2304 + lane * 32 + ((lane & 4) << 2);
        int ph = 0, b = 0;
#pragma unroll 1
        for (int ci = hw - 3; ci < 16; ci += 3) {
          const uint32_t bo = b ? OFF_F2F - OFF_STG : 0, bn = b ? 0 : OFF_F2F - OFF_STG;
          if (ci + 3 < 16) {
            while (__any_sync(~0u, (uint32_t)clock() - clk0 < HSTART + (ci + 3) * PACE)) __nanosleep(64);
            if (elect_one()) {
              mbar_expect(sbar + 8 * (b ^ 1), 2304 + 2048);
              tma2d(stg + bn, &P.tmK, 16 * cl, 1024 * rank + 64 * (ci + 3) - 8, sbar + 8 * (b ^ 1));
              tma2d(stg + bn + 2304, &P.tmV, 16 * cl, 1024 * rank + 64 * (ci + 3), sbar + 8 * (b ^ 1));
            }
          }
          if (ci >= 0) {
            mbar_wait(sbar + 8 * b, (ph >> b) & 1);
            ph ^= 1 << b;
#pragma unroll 1
            for (int grp = 0; grp < 2; grp++) {
#pragma unroll
              for (int cg = 0; cg < 2; cg++) {
                const uint32_t dst = mapa(xo + (ci >> 3) * 1024 + ((ci & 7) * 4 + 2 * grp) * 16, cg), xbar = mapa(BAR(B_XRAW), cg);
                uint32_t vv[4], kk[4][4];
                ldsm4t(vv, (va ^ (cg * 16)) + bo + grp * 1024);
#pragma unroll
                for (int rg = 0; rg < 4; rg++) ldsm4t(kk[rg], (ka ^ (cg * 16)) + bo + grp * 1024 + rg * 256);
#pragma unroll
                for (int rg = 0; rg < 4; rg++)
                  vv[rg] = hmul(hadd(hadd(hadd(hmul(kk[rg][3], tap[cg][3]), hmul(kk[rg][2], tap[cg][2])), hmul(kk[rg][1], tap[cg][1])), hmul(kk[rg][0], tap[cg][0])), vv[rg]);
                if (cg == rank) {
#pragma unroll
                  for (int rg = 0; rg < 4; rg++) asm volatile("st.shared.b32 [%0], %1;" ::"r"(dst + (rg & 1) * 512 + (rg >> 1) * 16), "r"(vv[rg]) : "memory");
                } else {
#pragma unroll
                  for (int rg = 0; rg < 4; rg++) st_async(dst + (rg & 1) * 512 + (rg >> 1) * 16, vv[rg], xbar);
                }
              }
            }
          }
          b ^= 1;
        }
      }
      if (lane == 0 && hw == 0) STAMP(3, 3);
      asm volatile("bar.sync 4, 96;" ::: "memory");
      if (hw == 0 && elect_one()) { mbar_expect(BAR(B_XT), 10240); bulk_ld(sb + OFF_F2F, P.img, 10240, BAR(B_XT)); }
      mbar_wait(BAR(B_XRAW), 0);
    }
    int e1 = 0;
#pragma unroll 1
    for (int n = hw < 0 ? 3 : 0; n < 4; n++) {
      const bool isH = n >= 3;
      const int c = isH ? (warp & 1) + 2 * (warp & 2) : hw + 3 * n;
      if (c < 8) {
        int ln;
        asm volatile("mov.u32 %0, %%laneid;" : "=r"(ln));
        uint8_t* dst = smem + (isH ? OFF_H + (c & 2) * 8192 + (c >> 2) * 8192 + (c & 1) * 4096 : OFF_XT + c * XT_STRIDE) + ((ln >> 4) * 512 + (ln & 15) * 16);
        const uint8_t* src0 = isH ? (const uint8_t*)P.h + (16 * cl + 8 * rank + c) * 4096 + ((ln & 15) * 32 + (ln & 16)) : dst;
        const uint8_t* src1 = src0 + (isH ? 512 : 256);
        uint32_t v[32];
#pragma unroll
        for (int i = 0; i < 8; i++) {
          const uint4 u = *(const uint4*)(((i & 1) ? src1 : src0) + (i >> 1) * 1024);
          v[4 * i] = u.x; v[4 * i + 1] = u.y; v[4 * i + 2] = u.z; v[4 * i + 3] = u.w;
        }
        if (isH) mbar_wait(BAR(B_XT), 0);
        const float f0 = __uint_as_float(v[0] << 16) + ((isH && ln == 0) ? *(const float*)(smem + OFF_D + 4 * c) : 0.f);
        const int e = norm_exp(v, f0);
        norm_cvt(v, f0, e);
        if (isH) mbar_wait(BAR(B_SFREE), 0);
        else if (ln == 0) smem[OFF_EX + c] = e;
        e1 = e;
#pragma unroll
        for (int i = 0; i < 8; i++)
          *(uint4*)(dst + (i >> 1) * 1024 + (i & 1) * 256) = make_uint4(v[4 * i], v[4 * i + 1], v[4 * i + 2], v[4 * i + 3]);
        if (n < 2 && elect_one()) {
          if (n == 0) mbar_expect(sbar, 4096);
          tma_q_ld(sb + OFF_STG + 2048 * c, &P.tmQ, 16 * cl, 2 * rank, c, sbar);
        }
      }
      if (n >= 2) {
        fence_async();
        __syncwarp();
        if (lane == 0) { mbar_arrive(BAR(isH ? B_H : B_XT)); STAMP(3, (isH ? 17 : 13) + hw); }
      }
    }
#define SLOT(tab, kb) (sb + ((uint32_t)((tab) >> (4 * (kb))) & 15) * 16384)
#define KT(kb) (!OLOC ? (kb) : (kb) == 0 ? hq : (kb) == hq ? 0 : (kb))
#define LOAD_B(kb) tma4d(SLOT(SLOT_B, kb), &P.tmWo, 0, ((kb) >> 3) * 32, 2 * (KT(kb) & 7), 4 * cb + 2 * rank, BAR(B_FULL2 + (kb)))
#define LOAD_A(kb) bulk_ld_mc(SLOT(SLOT_A, kb) + rank * 8192, P.o + rb * OBLK + KT(kb) * 1024 + rank * 512, 8192, BAR(B_FULL2 + (kb)))
    asm volatile("setmaxnreg.inc.sync.aligned.u32 %0;" ::"n"(504 - 2 * RC));
    {
    int tid;
    asm volatile("mov.u32 %0, %%tid.x;" : "=r"(tid));
    const int lane = tid & 31, g = lane >> 2, q = lane & 3;
    const unsigned epoch = *(volatile unsigned*)(smem + OFF_EPOCH);
    const uint32_t tag = ~epoch & 1;
    const int pi = hw < 2 ? 64 * mb - 288 + tid : 512 + 8 * (mb & 1) + (mb & 6) + (lane & 1);
    const float* psrc = P.part + hp * 8 * 2176 + 4 * pi;
    uint4 f[8];
    {
      const uint32_t s16 = (sb & 0x3FFFF) >> 4;
      const int t = tid & 127, c = 2 + (warp & 1) + 2 * (warp & 2);
      const uint4* hp4 = (const uint4*)(P.h + (16 * cl + 8 * rank + c) * 2048) + ((lane & 15) * 2 + (lane >> 4));
      uint32_t v[32];
#pragma unroll
      for (int i = 0; i < 8; i++) { const uint4 u = ld_na4(hp4 + i * 32); v[4 * i] = u.x; v[4 * i + 1] = u.y; v[4 * i + 2] = u.z; v[4 * i + 3] = u.w; }
      float kva[36];
#pragma unroll
      for (int mt = 0; mt < 2; mt++) {
        mbar_wait(BAR(B_PKRDY + mt), 0);
        wg_fence();
#pragma unroll
        for (int ks = 0; ks < 8; ks++) {
          const uint32_t o = (ks >> 2) * 1024 + mt * 512 + (ks & 3) * 128, vb = (2 * STAGE_BYTES >> 4) + o;
          wgmma_ss_n72<1, 1>(kva, dsc(s16 + o + (1 << 16), SW128), dsc(s16 + vb + (((OFF_ONES >> 4) - vb) << 16), SW128), (mt | ks) != 0);
        }
        wg_commit();
        if (mt == 0 && hw < 0) {
          mbar_wait(BAR(B_G1DONE), 0);
          if (elect_one()) {
#pragma unroll
            for (int kb = 0; kb < BEARLY; kb++) { mbar_expect(BAR(B_FULL2 + kb), 16384); LOAD_B(kb); }
          }
        }
      }
      float* pdst = P.part + (hp * 8 + mb) * 2176 + t * 4;
      float* zdst = P.part + (hp * 8 + mb) * 2176 + 2048 + (t >> 1);
      asm volatile("" : "+l"(pdst), "+l"(zdst));
      wg_wait<0>();
      keep(kva);
      if (hw < 1) {
#pragma unroll
        for (int c = 0; c < 4; c++) st_tag4(pdst + c * 512, kva[4 * c], kva[4 * c + 1], kva[4 * c + 2], kva[4 * c + 3], tag);
      } else {
#pragma unroll
        for (int c = 4; c < 8; c++) st_tag4(pdst + (c - 4) * 512, kva[4 * c], kva[4 * c + 1], kva[4 * c + 2], kva[4 * c + 3], tag);
      }
      const float z2 = __shfl_down_sync(~0u, kva[32], 4), z3 = __shfl_down_sync(~0u, kva[34], 4);
      if (!(lane & 7)) st_tag4(zdst, kva[32], kva[34], z2, z3, tag);
      if (lane == 0) mbar_arrive(BAR(B_PKFREE));
      const uint32_t cst = clock();
      if (hw == 0 && lane == 0) STAMP(3, 24);
      const float f0 = __uint_as_float(v[0] << 16) + (lane == 0 ? *(const float*)(smem + OFF_D + 4 * c) : 0.f);
      const int e = norm_exp(v, f0);
      norm_cvt(v, f0, e);
      if (hw >= 0) {
        while (__any_sync(~0u, (uint32_t)clock() - cst < PD1)) __nanosleep(20);
        if (hw == 0 && lane == 0) STAMP(3, 20);
#pragma unroll
        for (int p = 0; p < 8; p++) f[p] = ld_rlx4(psrc + p * 2176);
      }
      uint8_t* dst = smem + OFF_H + 16384 + (warp & 3) * 4096 + (lane >> 4) * 512 + (lane & 15) * 16;
#pragma unroll
      for (int i = 0; i < 8; i++)
        *(uint4*)(dst + (i >> 1) * 1024 + (i & 1) * 256) = make_uint4(v[4 * i], v[4 * i + 1], v[4 * i + 2], v[4 * i + 3]);
      if (lane < 4) {
        const int cc = c - (lane & 2);
        st_async(mapa(sb + OFF_SCALE + (8 * rank + cc) * 4, lane & 1), min(max(((lane & 2) ? e1 : e) + smem[OFF_EX + cc] - 124, 1), 254) << 23, mapa(BAR(B_Y), lane & 1));
      }
    }
#define H2_READY() do { fence_async(); __syncwarp(); if (lane == 0) mbar_arrive(BAR(B_H2)); } while (0)
    if (warp == 8) {
      H2_READY();
      mbar_wait(BAR(B_PKFREE), 0);
      {
        const uint32_t c0 = clock();
#pragma unroll 1
        for (int i = 0; i < 2 * NPRE - 2 * BEARLY; i++) {
          const int kb = (i >> 1) + BEARLY;
          while (__any_sync(~0u, (uint32_t)clock() - c0 < i * BPACE)) __nanosleep(32);
          if (elect_one()) {
            if (!(i & 1)) mbar_expect(BAR(B_FULL2 + kb), 16384);
            tma4d(SLOT(SLOT_B, kb) + (i & 1) * 8192, &P.tmWo1, 0, 0, 2 * KT(kb), 4 * cb + 2 * rank + (i & 1), BAR(B_FULL2 + kb));
            if (i == 0) mbar_expect(BAR(B_Q), 8192);
            if (i < 4) tma_q_ld(sb + OFF_SPARE + 2048 * i, &P.tmQ, 16 * cl, 2 * rank + (i >> 1), (i + 6) & 7, BAR(B_Q));
          }
        }
      }
      if (elect_one()) { MAP_PF(tmOA); MAP_PF(tmOB); }
      if (lane == 0) STAMP(2, 2);
      if (OLOC) {
        if (elect_one()) mbar_expect(BAR(B_FULL2), 16384);
        mbar_wait(BAR(B_OLOC), 0);
        asm volatile("fence.acquire.cluster;\nfence.proxy.async.global;" ::: "memory");
        if (elect_one()) LOAD_A(0);
      }
      mbar_wait(BAR(B_AFREE), 0);
      if (elect_one()) mbar_expect(BAR(B_FULL2 + OLOC), 16384);
      {
        const uint32_t dst = SLOT(SLOT_A, OLOC) + rank * 8192;
        const uint4* src = P.o + rb * OBLK + KT(OLOC) * 1024 + rank * 512;
        poll_ge(OCNT(rb, 0), 16 * (epoch + 1));
        asm volatile("fence.proxy.async.global;" ::: "memory");
        if (lane == 0) STAMP(2, 3);
        if (elect_one()) bulk_ld_mc(dst, src, 8192, BAR(B_FULL2 + OLOC));
        if (lane == 0) STAMP(3, 23);
      }
#pragma unroll 1
      for (int kb = 1 + OLOC; kb < NPRE; kb++) {
        mbar_wait(BAR(kb < 4 ? B_AFREE + kb - 1 : B_CONS2), 0);
        if (elect_one()) { mbar_expect(BAR(B_FULL2 + kb), 16384); LOAD_A(kb); }
      }
#pragma unroll 1
      for (int kb = NPRE; kb < 16; kb++) {
        mbar_wait(BAR(B_CONS2 + kb - 5), 0);
        if (kb == 8) mbar_wait(BAR(B_O1RDY), 0);
        if (elect_one()) { mbar_expect(BAR(B_FULL2 + kb), 32768); LOAD_A(kb); LOAD_B(kb); }
      }
      if (lane == 0) { EPOCH = epoch + 1; STAMP(2, 5); }
    } else {
      {
#pragma unroll 1
        for (int n = 0; __any_sync(~0u, stale8(f, tag) & 1); n++) {
#pragma unroll
          for (int p = 0; p < 8; p++) ld_stale4(f[p], psrc + p * 2176, tag);
          if (n > SPIN_LIMIT) __trap();
        }
        float s0 = 0.f, s1 = 0.f, s2 = 0.f, s3 = 0.f;
#pragma unroll
        for (int p = 0; p < 8; p++) { s0 += __uint_as_float(f[p].x); s1 += __uint_as_float(f[p].y); s2 += __uint_as_float(f[p].z); s3 += __uint_as_float(f[p].w); }
        if (hw < 2 || lane < 2) st_tag4(P.kv + hp * 2176 + (4 * pi), s0, s1, s2, s3, tag);
      }
      const uint32_t cs2 = clock();
      if (lane == 0 && hw == 0) STAMP(3, 8);
      H2_READY();
      if (hw == 2) {
        unsigned* cnt = OCNT(2 * mb + lane, 0);
#pragma unroll 1
        for (int hh = 0; hh < 2; hh++) {
          mbar_wait(BAR(hh ? B_ODONE1 : B_ODONE), 0);
          if (lane < 2) asm volatile("red.release.gpu.global.add.u32 [%0], 1;" ::"l"(cnt) : "memory");
          if (OLOC && hh == 0 && lane < 2) mbar_arrive_cl(BAR(B_OLOC), lane);
          cnt += 32;
          if (lane == 0) STAMP(3, hh ? 6 : 7);
        }
        poll_ge(OCNT(rb, 1), 16 * (epoch + 1));
        asm volatile("fence.proxy.async.global;" ::: "memory");
        if (lane == 0) { mbar_arrive(BAR(B_O1RDY)); STAMP(2, 4); }
        __syncwarp();
      } else {
        const int t = tid - 288;
        const float* src = P.kv + hp * 2176 + 4 * (t + 32 * hw);
        const float* zsrc = P.kv + hp * 2176 + (2048 + (t & 48) + 2 * (lane & 6));
        mbar_wait(BAR(B_PKFREE), 0);
        while (__any_sync(~0u, (uint32_t)clock() - cs2 < PD2)) __nanosleep(20);
        uint4 zp = ld_rlx4(zsrc);
#pragma unroll
        for (int p = 0; p < 8; p++) f[p] = ld_rlx4(src + 4 * ((p & 3) * 128 + (p >> 2) * 32));
        if (!opaque_true()) __trap();
#pragma unroll 1
        for (int n = 0; __any_sync(~0u, (stale8(f, tag) | (zp.x ^ tag)) & 1); n++) {
          ld_stale4(zp, zsrc, tag);
#pragma unroll
          for (int p = 0; p < 8; p++) ld_stale4(f[p], src + 4 * ((p & 3) * 128 + (p >> 2) * 32), tag);
          if (n > SPIN_LIMIT) __trap();
        }
#define PK2U(a, b) pk2(__uint_as_float(a), __uint_as_float(b))
        const uint32_t zf = (lane & 1) ? ((lane & 8) ? zp.w : zp.z) : ((lane & 8) ? zp.y : zp.x);
        const uint32_t zz = PK2U(zf, zf);
        *(uint4*)(smem + OFF_KVB + hw * 2560 + 2048 + lane * 16) = make_uint4(zz, zz, zz, zz);
#pragma unroll
        for (int hh = 0; hh < 2; hh++) {
          const uint4* ff = &f[4 * hh];
          uint8_t* dst = smem + OFF_KVB + hw * 2560 + q * 512 + (16 * hh + g) * 16;
          *(uint4*)dst = make_uint4(PK2U(ff[0].x, ff[0].y), PK2U(ff[1].x, ff[1].y), PK2U(ff[2].x, ff[2].y), PK2U(ff[3].x, ff[3].y));
          *(uint4*)(dst + 128) = make_uint4(PK2U(ff[0].z, ff[0].w), PK2U(ff[1].z, ff[1].w), PK2U(ff[2].z, ff[2].w), PK2U(ff[3].z, ff[3].w));
        }
        fence_async();
        __syncwarp();
        if (lane == 0) { mbar_arrive(BAR(hw ? B_KV1 : B_KV)); if (hw == 0) STAMP(3, 9); }
      }
#define QBUF(ci) (sb + 2048 * (ci) + ((ci) < 6 ? OFF_STG : (ci) < 10 ? OFF_SPARE - 6 * 2048 : OFF_F2F - 10 * 2048))
      mbar_wait(BAR(B_Y), 0);
      if (elect_one()) {
        mbar_expect(sbar + 8, 4096);
#pragma unroll 1
        for (int ci = hw ? hw + 9 : 12; ci < 16; ci += 3) tma_q_ld(QBUF(ci), &P.tmQ, 16 * cl, 2 * rank + 1, ci & 7, sbar + 8);
      }
      mbar_wait(BAR(B_Q), 0);
      mbar_wait(sbar, hw == 0);
      {
        const uint2 f0 = *(const uint2*)(smem + OFF_SCALE + 8 * q), f1 = *(const uint2*)(smem + OFF_SCALE + 32 + 8 * q);
        const uint32_t sc0 = __byte_perm(f0.x, f0.y, 0x7632), sc1 = __byte_perm(f1.x, f1.y, 0x7632);
        const uint32_t yl = sb + OFF_XT + (lane & 7) * XT_STRIDE + (lane >> 3) * 16;
#pragma unroll 1
        for (int ci = hw; ci < 16; ci += 3) {
          const uint32_t qb = QBUF(ci);
          if (ci >= 10) mbar_wait(sbar + 8, 1);
          uint32_t yy[4][4], qq[4][4];
          const uint32_t qa = qb + ((lane & 25) + (lane & 2) * 2 + ((lane >> 1) & 2)) * 32 + ((lane & 2) << 3);
#pragma unroll
          for (int u = 0; u < 4; u++) {
            ldsm4t(yy[u], yl + (u & 1) * 2048 + (ci >> 3) * 1024 + (u >> 1) * 512 + (ci & 7) * 64);
            ldsm4(qq[u], (qa ^ ((u & 1) * 16)) + (u >> 1) * 1024);
          }
          if (!opaque_true()) __trap();
#pragma unroll
          for (int u = 0; u < 4; u++) {
#pragma unroll
            for (int m = 0; m < 4; m++) {
              const float2 f = __half22float2(*(const __half2*)&yy[u][m]);
              qq[u][m] = hmul(qq[u][m], hmul(pk2(f.x, f.y), (u & 1) ? sc1 : sc0));
            }
            stsm4((qa ^ ((u & 1) * 16)) + (u >> 1) * 1024, qq[u][0], qq[u][1], qq[u][2], qq[u][3]);
          }
          fence_async();
          __syncwarp();
          if (elect_one()) tma_q_st(&P.tmOA, qb, 16 * cl, 2 * rank + (ci >> 3), ci & 7);
        }
        asm volatile("cp.async.bulk.commit_group;\ncp.async.bulk.wait_group.read 0;" ::: "memory");
      }
      if (lane == 0) STAMP(3, 10 + hw);
    }
    }
  }
}

typedef CUresult (*EncodeFn)(CUtensorMap*, CUtensorMapDataType, cuuint32_t, void*, const cuuint64_t*, const cuuint64_t*,
                             const cuuint32_t*, const cuuint32_t*, CUtensorMapInterleave, CUtensorMapSwizzle,
                             CUtensorMapL2promotion, CUtensorMapFloatOOBfill);

static void enc(EncodeFn fn, CUtensorMap* m, const void* p, int rank, const cuuint64_t* dims, const cuuint64_t* strides,
                const cuuint32_t* box, CUtensorMapSwizzle swz, CUtensorMapL2promotion promo) {
  cuuint32_t es[5] = {1, 1, 1, 1, 1};
  fn(m, CU_TENSOR_MAP_DATA_TYPE_BFLOAT16, rank, (void*)p, dims, strides, box, es, CU_TENSOR_MAP_INTERLEAVE_NONE, swz, promo,
     CU_TENSOR_MAP_FLOAT_OOB_FILL_NONE);
}

extern "C" void kernel_launch(void* const* d_in, const int* in_sizes, int n_in, void* d_out, int out_size) {
  void* fp = nullptr;
  cudaDriverEntryPointQueryResult qr;
  cudaGetDriverEntryPoint("cuTensorMapEncodeTiled", &fp, cudaEnableDefault, &qr);
  EncodeFn fn = (EncodeFn)fp;
  Params P;
  P.shift_k = (const __nv_bfloat16*)d_in[3]; P.h = (const __nv_bfloat16*)d_in[4]; P.D = (const __nv_bfloat16*)d_in[5];
  P.q = (const __nv_bfloat16*)d_in[0];
  cudaGetSymbolAddress((void**)&P.part, g_part); cudaGetSymbolAddress((void**)&P.kv, g_kv); cudaGetSymbolAddress((void**)&P.o, g_o);
  cudaGetSymbolAddress((void**)&P.thr, c_thr); cudaGetSymbolAddress((void**)&P.img, c_img);
  P.x = (const __nv_bfloat16*)d_in[6]; P.w = (const __nv_bfloat16*)d_in[7]; P.wo = (const __nv_bfloat16*)d_in[8];
  const CUtensorMapSwizzle S128 = CU_TENSOR_MAP_SWIZZLE_128B, S32 = CU_TENSOR_MAP_SWIZZLE_32B;
  const CUtensorMapL2promotion P0 = CU_TENSOR_MAP_L2_PROMOTION_NONE, P128 = CU_TENSOR_MAP_L2_PROMOTION_L2_128B;
  { cuuint64_t d[2] = {1024, 2048}, s[1] = {2048}; cuuint32_t b[2] = {64, 128}; enc(fn, &P.tmX, d_in[6], 2, d, s, b, S128, P128); }
  { cuuint64_t d[2] = {1024, 2048}, s[1] = {2048}; cuuint32_t b[2] = {64, 64}; enc(fn, &P.tmX0, d_in[6], 2, d, s, b, S128, P128); }
  { cuuint64_t d[3] = {1024, 1024, 3}, s[2] = {6144, 2048}; cuuint32_t b[3] = {64, 64, 3}; enc(fn, &P.tmW, d_in[7], 3, d, s, b, S128, P128); }
  { cuuint64_t d[4] = {64, 64, 16, 16}, s[3] = {2048, 131072, 128}; cuuint32_t b[4] = {64, 32, 2, 2}; enc(fn, &P.tmWo, d_in[8], 4, d, s, b, S128, P128); }
  { cuuint64_t d[4] = {64, 64, 16, 16}, s[3] = {2048, 131072, 128}; cuuint32_t b[4] = {64, 32, 2, 1}; enc(fn, &P.tmWo1, d_in[8], 4, d, s, b, S128, P128); }
  { cuuint64_t d[2] = {1024, 2048}, s[1] = {2048}; cuuint32_t b[2] = {16, 72}; enc(fn, &P.tmK, d_in[1], 2, d, s, b, S32, P128); }
  { cuuint64_t d[2] = {1024, 2048}, s[1] = {2048}; cuuint32_t b[2] = {16, 64}; enc(fn, &P.tmV, d_in[2], 2, d, s, b, S32, P128); }
  { cuuint64_t d[5] = {1024, 4, 2, 32, 8}, s[4] = {32768, 16384, 131072, 2048}; cuuint32_t b[5] = {16, 4, 2, 8, 1}; enc(fn, &P.tmQ, d_in[0], 5, d, s, b, S32, P128); }
  { cuuint64_t d[5] = {1024, 4, 2, 32, 8}, s[4] = {65536, 32768, 262144, 4096}; cuuint32_t b[5] = {16, 4, 2, 8, 1}; enc(fn, &P.tmOA, d_out, 5, d, s, b, S32, P0); }
  { cuuint64_t d[2] = {2048, 2048}, s[1] = {4096}; cuuint32_t b[2] = {64, 16}; enc(fn, &P.tmOB, d_out, 2, d, s, b, S128, P0); }
  cudaFuncSetAttribute(fused_kernel, cudaFuncAttributeMaxDynamicSharedMemorySize, SMEM_TOTAL);
  fused_kernel<<<128, 384, SMEM_TOTAL>>>(P);
}
```

```cpp
#include <cuda_runtime.h>
#include <cuda_bf16.h>
#include <cuda_fp16.h>
#include <cuda.h>
#include <stdint.h>

template<int TA, int TB, int SA=1> __device__ __forceinline__ void wgmma_ss_n192(float (&d)[96], uint64_t da, uint64_t db, int scale_d) {
  asm volatile("{\n.reg .pred p;\nsetp.ne.b32 p, %98, 0;\n"
    "wgmma.mma_async.sync.aligned.m64n192k16.f32.bf16.bf16 {%0, %1, %2, %3, %4, %5, %6, %7, %8, %9, %10, %11, %12, %13, %14, %15, %16, %17, %18, %19, %20, %21, %22, %23, %24, %25, %26, %27, %28, %29, %30, %31, %32, %33, %34, %35, %36, %37, %38, %39, %40, %41, %42, %43, %44, %45, %46, %47, %48, %49, %50, %51, %52, %53, %54, %55, %56, %57, %58, %59, %60, %61, %62, %63, %64, %65, %66, %67, %68, %69, %70, %71, %72, %73, %74, %75, %76, %77, %78, %79, %80, %81, %82, %83, %84, %85, %86, %87, %88, %89, %90, %91, %92, %93, %94, %95}, %96, %97, p, %101, 1, %99, %100;\n}\n"
    : "+f"(d[0]), "+f"(d[1]), "+f"(d[2]), "+f"(d[3]), "+f"(d[4]), "+f"(d[5]), "+f"(d[6]), "+f"(d[7]), "+f"(d[8]), "+f"(d[9]), "+f"(d[10]), "+f"(d[11]), "+f"(d[12]), "+f"(d[13]), "+f"(d[14]), "+f"(d[15]), "+f"(d[16]), "+f"(d[17]), "+f"(d[18]), "+f"(d[19]), "+f"(d[20]), "+f"(d[21]), "+f"(d[22]), "+f"(d[23]), "+f"(d[24]), "+f"(d[25]), "+f"(d[26]), "+f"(d[27]), "+f"(d[28]), "+f"(d[29]), "+f"(d[30]), "+f"(d[31]), "+f"(d[32]), "+f"(d[33]), "+f"(d[34]), "+f"(d[35]), "+f"(d[36]), "+f"(d[37]), "+f"(d[38]), "+f"(d[39]), "+f"(d[40]), "+f"(d[41]), "+f"(d[42]), "+f"(d[43]), "+f"(d[44]), "+f"(d[45]), "+f"(d[46]), "+f"(d[47]), "+f"(d[48]), "+f"(d[49]), "+f"(d[50]), "+f"(d[51]), "+f"(d[52]), "+f"(d[53]), "+f"(d[54]), "+f"(d[55]), "+f"(d[56]), "+f"(d[57]), "+f"(d[58]), "+f"(d[59]), "+f"(d[60]), "+f"(d[61]), "+f"(d[62]), "+f"(d[63]), "+f"(d[64]), "+f"(d[65]), "+f"(d[66]), "+f"(d[67]), "+f"(d[68]), "+f"(d[69]), "+f"(d[70]), "+f"(d[71]), "+f"(d[72]), "+f"(d[73]), "+f"(d[74]), "+f"(d[75]), "+f"(d[76]), "+f"(d[77]), "+f"(d[78]), "+f"(d[79]), "+f"(d[80]), "+f"(d[81]), "+f"(d[82]), "+f"(d[83]), "+f"(d[84]), "+f"(d[85]), "+f"(d[86]), "+f"(d[87]), "+f"(d[88]), "+f"(d[89]), "+f"(d[90]), "+f"(d[91]), "+f"(d[92]), "+f"(d[93]), "+f"(d[94]), "+f"(d[95])
    : "l"(da), "l"(db), "r"(scale_d), "n"(TA), "n"(TB), "n"(SA));
}
template<int TA, int TB, int SA=1> __device__ __forceinline__ void wgmma_ss_n128(float (&d)[64], uint64_t da, uint64_t db, int scale_d) {
  asm volatile("{\n.reg .pred p;\nsetp.ne.b32 p, %66, 0;\n"
    "wgmma.mma_async.sync.aligned.m64n128k16.f32.bf16.bf16 {%0, %1, %2, %3, %4, %5, %6, %7, %8, %9, %10, %11, %12, %13, %14, %15, %16, %17, %18, %19, %20, %21, %22, %23, %24, %25, %26, %27, %28, %29, %30, %31, %32, %33, %34, %35, %36, %37, %38, %39, %40, %41, %42, %43, %44, %45, %46, %47, %48, %49, %50, %51, %52, %53, %54, %55, %56, %57, %58, %59, %60, %61, %62, %63}, %64, %65, p, %69, 1, %67, %68;\n}\n"
    : "+f"(d[0]), "+f"(d[1]), "+f"(d[2]), "+f"(d[3]), "+f"(d[4]), "+f"(d[5]), "+f"(d[6]), "+f"(d[7]), "+f"(d[8]), "+f"(d[9]), "+f"(d[10]), "+f"(d[11]), "+f"(d[12]), "+f"(d[13]), "+f"(d[14]), "+f"(d[15]), "+f"(d[16]), "+f"(d[17]), "+f"(d[18]), "+f"(d[19]), "+f"(d[20]), "+f"(d[21]), "+f"(d[22]), "+f"(d[23]), "+f"(d[24]), "+f"(d[25]), "+f"(d[26]), "+f"(d[27]), "+f"(d[28]), "+f"(d[29]), "+f"(d[30]), "+f"(d[31]), "+f"(d[32]), "+f"(d[33]), "+f"(d[34]), "+f"(d[35]), "+f"(d[36]), "+f"(d[37]), "+f"(d[38]), "+f"(d[39]), "+f"(d[40]), "+f"(d[41]), "+f"(d[42]), "+f"(d[43]), "+f"(d[44]), "+f"(d[45]), "+f"(d[46]), "+f"(d[47]), "+f"(d[48]), "+f"(d[49]), "+f"(d[50]), "+f"(d[51]), "+f"(d[52]), "+f"(d[53]), "+f"(d[54]), "+f"(d[55]), "+f"(d[56]), "+f"(d[57]), "+f"(d[58]), "+f"(d[59]), "+f"(d[60]), "+f"(d[61]), "+f"(d[62]), "+f"(d[63])
    : "l"(da), "l"(db), "r"(scale_d), "n"(TA), "n"(TB), "n"(SA));
}
template<int TA, int TB, int SA=1> __device__ __forceinline__ void wgmma_ss_n72(float (&d)[36], uint64_t da, uint64_t db, int scale_d) {
  asm volatile("{\n.reg .pred p;\nsetp.ne.b32 p, %38, 0;\n"
    "wgmma.mma_async.sync.aligned.m64n72k16.f32.bf16.bf16 {%0, %1, %2, %3, %4, %5, %6, %7, %8, %9, %10, %11, %12, %13, %14, %15, %16, %17, %18, %19, %20, %21, %22, %23, %24, %25, %26, %27, %28, %29, %30, %31, %32, %33, %34, %35}, %36, %37, p, %41, 1, %39, %40;\n}\n"
    : "+f"(d[0]), "+f"(d[1]), "+f"(d[2]), "+f"(d[3]), "+f"(d[4]), "+f"(d[5]), "+f"(d[6]), "+f"(d[7]), "+f"(d[8]), "+f"(d[9]), "+f"(d[10]), "+f"(d[11]), "+f"(d[12]), "+f"(d[13]), "+f"(d[14]), "+f"(d[15]), "+f"(d[16]), "+f"(d[17]), "+f"(d[18]), "+f"(d[19]), "+f"(d[20]), "+f"(d[21]), "+f"(d[22]), "+f"(d[23]), "+f"(d[24]), "+f"(d[25]), "+f"(d[26]), "+f"(d[27]), "+f"(d[28]), "+f"(d[29]), "+f"(d[30]), "+f"(d[31]), "+f"(d[32]), "+f"(d[33]), "+f"(d[34]), "+f"(d[35])
    : "l"(da), "l"(db), "r"(scale_d), "n"(TA), "n"(TB), "n"(SA));
}
template<int TB, int SA=1> __device__ __forceinline__ void wgmma_rs_n40(float (&d)[20], uint32_t a0, uint32_t a1, uint32_t a2, uint32_t a3, uint64_t db, int scale_d) {
  asm volatile("{\n.reg .pred p;\nsetp.ne.b32 p, %25, 0;\n"
    "wgmma.mma_async.sync.aligned.m64n40k16.f32.bf16.bf16 {%0, %1, %2, %3, %4, %5, %6, %7, %8, %9, %10, %11, %12, %13, %14, %15, %16, %17, %18, %19}, {%20, %21, %22, %23}, %24, p, %27, 1, %26;\n}\n"
    : "+f"(d[0]), "+f"(d[1]), "+f"(d[2]), "+f"(d[3]), "+f"(d[4]), "+f"(d[5]), "+f"(d[6]), "+f"(d[7]), "+f"(d[8]), "+f"(d[9]), "+f"(d[10]), "+f"(d[11]), "+f"(d[12]), "+f"(d[13]), "+f"(d[14]), "+f"(d[15]), "+f"(d[16]), "+f"(d[17]), "+f"(d[18]), "+f"(d[19])
    : "r"(a0), "r"(a1), "r"(a2), "r"(a3), "l"(db), "r"(scale_d), "n"(TB), "n"(SA));
}
template<int TB> __device__ __forceinline__ void wgmma_hrs_n64(uint32_t (&d)[16], uint32_t a0, uint32_t a1, uint32_t a2, uint32_t a3, uint64_t db, int scale_d) {
  asm volatile("{\n.reg .pred p;\nsetp.ne.b32 p, %21, 0;\n"
    "wgmma.mma_async.sync.aligned.m64n64k16.f16.f16.f16 {%0, %1, %2, %3, %4, %5, %6, %7, %8, %9, %10, %11, %12, %13, %14, %15}, {%16, %17, %18, %19}, %20, p, 1, 1, %22;\n}\n"
    : "+r"(d[0]), "+r"(d[1]), "+r"(d[2]), "+r"(d[3]), "+r"(d[4]), "+r"(d[5]), "+r"(d[6]), "+r"(d[7]), "+r"(d[8]), "+r"(d[9]), "+r"(d[10]), "+r"(d[11]), "+r"(d[12]), "+r"(d[13]), "+r"(d[14]), "+r"(d[15])
    : "r"(a0), "r"(a1), "r"(a2), "r"(a3), "l"(db), "r"(scale_d), "n"(TB));
}
template<int TB> __device__ __forceinline__ void wgmma_hrs_n32(uint32_t (&d)[8], uint32_t a0, uint32_t a1, uint32_t a2, uint32_t a3, uint64_t db, int scale_d) {
  asm volatile("{\n.reg .pred p;\nsetp.ne.b32 p, %13, 0;\n"
    "wgmma.mma_async.sync.aligned.m64n32k16.f16.f16.f16 {%0, %1, %2, %3, %4, %5, %6, %7}, {%8, %9, %10, %11}, %12, p, 1, 1, %14;\n}\n"
    : "+r"(d[0]), "+r"(d[1]), "+r"(d[2]), "+r"(d[3]), "+r"(d[4]), "+r"(d[5]), "+r"(d[6]), "+r"(d[7])
    : "r"(a0), "r"(a1), "r"(a2), "r"(a3), "l"(db), "r"(scale_d), "n"(TB));
}

__device__ __align__(128) const uint32_t c_thr[1536] = {
  0x33fb33ff,0xa49c9de4,0x33273352,0xaf2cae76,0x33e233f1,0xa96ca7bd,0x32c432f7,0xb045afdd,0x33b733cf,0xac3eaaf7,0x3250328c,0xb0eab099,
  0x3378339a,0xadbcacff,0x31cd3211,0xb182b137,0x33d033fb,0xaadea46a,0x299e2d17,0xb3e0b396,0x32fb337a,0xafd2adb1,0xa78b1f76,0xb3f2b3ff,
  0x318b3254,0xb1c5b0e5,0xae6bac32,0xb354b3b8,0x2f4230a3,0xb321b285,0xb133b040,0xb215b2c7,0x337c33f2,0xada5a759,0xb179afc8,0xb1d6b2fe,
  0x31463293,0xb204b08e,0xb394b2ba,0xad23b055,0x2b402f4e,0xb3cbb31e,0xb3e4b3f9,0x293ba533,0xac269c52,0xb3bab400,0xb258b357,0x30e02e5f,
  0x330133e5,0xafbda922,0xb3f3b3c9,0x2727ab59,0x2deb314a,0xb36fb200,0xb194b32f,0x31bc2f0a,0xacdb2084,0xb39fb3ff,0xa565aea4,0x33f93347,
  0xb2b6b0db,0xb05ab25c,0x30892c1a,0x329733bc,0x326033d4,0xb0d6aa94,0xb00ab29b,0x32e83084,0x20e82f64,0xb3feb318,0x2d8da597,0x338133f8,
  0xb1fcae48,0xb14fb35c,0x339031b8,0x2d3a3199,0xb3e6b3ae,0x2909ac7b,0x32d133f4,0xb030a6f5,0x319d33bf,0xb1b3ac02,0x2e3ca874,0x335e33ec,
  0xacc32b89,0xb3a3b3c6,0x33f83276,0x25c930b7,0xb3dcb1f8,0xaa01b154,0x30653335,0xb2b0aef4,0xb107b383,0x32392d81,0xafa6214d,0xb307b3fe,
  0x30bc33a5,0xb273acb7,0x33c5311b,0x2ba23229,0xb0cc94b6,0xb267b400,0x30153360,0xb2e1ae31,0xb385b3ab,0x2d76ac93,0xb166a691,0xb1e7b3f5,
  0x22deb06a,0x33fd32ac,0xb337b3da,0x2ee8aa19,0x2f853387,0xb310ad6a,0x322d33fe,0xb1162216,0xb2a9abd3,0xb06fb3c2,0xb07428a6,0xb2a5b3ea,
  0xb111b3e9,0x323128be,0xb30db3c3,0x2f90abba,0x31aa227a,0x31a633fd,0x2e25ad5e,0x33633389,0x2d6a3365,0xb387ae1a,0xa21631aa,0xb3feb1a6,
  0xb3c2af85,0xabd3b310,0xb3eab22d,0x28a6b116,0xa8beb2a9,0x33e9306f,0x2bbab074,0x33c332a5,0x33fd3111,0x227a3231,0x3389330d,0xad5e2f90,
  0x2a63333f,0xb3d7aec6,0xb2a2a1b1,0xb07ab3fe,0xb3f7b158,0x25fbb1f4,0xacb7b38b,0x33a52d52,0x2e0eb025,0x336832d8,0x340030bc,0x14b63273,
  0x323533c0,0xb10c2beb,0xac9330cc,0xb3abb267,0x23433316,0xb3fdaf6f,0xb38eb225,0x2d46b11f,0xb342b29e,0x2ebbb07f,0x31e3aa7c,0x316b33d6,
  0x3264a6c3,0x30d133f5,0x2c0233ac,0xb3bfac87,0x28f0336a,0xb3e7ae02,0xb3c6b19d,0x2b89b1b3,0xa59732e8,0xb3f8b00a,0xaccfb3ed,0x33a1285b,
  0xb1b8b381,0x3199ad8d,0x336c31df,0xadf73170,0x33f42d3a,0x26f53390,0xb30423a7,0xafb2b3fc,0xb05f3030,0xb2b3b2d1,0x29e8b27a,0x33dd30b2,
  0xab5932b6,0xb3c9b05a,0x30adb089,0x327e3297,0xaf0ab3f3,0x332fa727,0x240633b0,0xb3fcac6f,0x33473194,0xaea431bc,0xb174b359,0x31daae54,
  0xb3bca565,0xac1ab3f9,0x33ee2f59,0xa842331b,0xaddf3281,0xb371b0a8,0x34002b40,0x1c5233cb,0xa759b3ef,0x33f22829,0xb2fe2c26,0xafc8b3ba,
  0x308e337c,0xb2932da5,0x3055b179,0x32ba31d6,0xb31eb146,0x2f4eb204,0xa5333394,0xb3f9ad23,0xaff33249,0xb2f1b0f3,0x30e532fb,0xb2542fd2,
  0x2b28b373,0x33cc2dd4,0xb285b18b,0x30a3b1c5,0x246a33fa,0xb3fba500,0x33962f42,0xad173321,0xadb1b3d0,0x337aaade,0xb3ffa99e,0x1f76b3e0,
  0xb0ee320d,0xb24db13c,0xac4b3398,0xb3b5ad0b,0x304ab289,0x32c1309e,0x2985b3ce,0x33e12b0f,0xaf3732f4,0xb324afe8,0xa4ce33f0,0xb3faa7ef,
  0x2dc8b34f,0x33762e82,0x9de4b3ff,0x33ff1ead,0xb1c931cd,0xb186b182,0xb3762e82,0xadc8b34f,0x324db13c,0x30ee320d,0x33b5ad0b,0x2c4b3398,
  0xb2c1309e,0xb04ab289,0xb3e12b0f,0xa985b3ce,0x3324afe8,0x2f3732f4,0x33faa7ef,0x24ce33f0,0xb285318b,0xb0a3b1c5,0xb2c7ae6b,0x3040b354,
  0x3396af42,0x2d173321,0x31413133,0xb2093215,0xb3ff299e,0x9f76b3e0,0xae8db2bd,0x334cb050,0x33b8278b,0xac3233f2,0x281033b3,0xb3ef2c57,
  0xb31e3146,0xaf4eb204,0xa533b394,0x33f9ad23,0x3400ab40,0x9c5233cb,0xae5f33e4,0xb357a93b,0xb2feac26,0x2fc8b3ba,0x3245b258,0x30f830e0,
  0x30553179,0xb2ba31d6,0xb3df2e99,0xa9b6b34a,0xb39230fd,0xad2fb241,0x3200b301,0x314a2fbd,0x337f1b11,0xad993400,0xb3ff2deb,0xa084b36f,
  0xb005b129,0x32ebb21d,0x325c2cdb,0xb0db339f,0xa92233de,0xb3e529cf,0xab59b2b6,0x33c9b05a,0xb3dd30b2,0xa9e8b27a,0x33d4ab71,0xaa9433c8,
  0x32212c0e,0xb12433bd,0xaf64b0d6,0x3318b260,0x197fb345,0x3400aeaf,0xae4833fe,0xb35c20e8,0xb23d3332,0xb102aeff,0x33aeb14f,0x2c7b31fc,
  0xb3fe3065,0xa14db2b0,0x2ebb307f,0xb342329e,0x300f2fa6,0xb2e53307,0x30d1b3f5,0x326426c3,0x302ab400,0x32d517db,0xb3e72e02,0x28f0b36a,
  0xb3fd2f6f,0x2343b316,0x2d46311f,0xb38e3225,0xb3f53015,0x2691b2e1,0xaf9b33eb,0xb30a288d,0x2a193166,0xb3da31e7,0x33d7aec6,0xaa63333f,
  0x3313b337,0x2f7a2ee8,0xa5fbb1f4,0x33f7b158,0xb1a1a8d7,0x31afb3e8,0xb36832d8,0xae0eb025,0xb3c22f85,0x2bd3b310,0xb3ea322d,0xa8a6b116,
  0xa8be32a9,0xb3e9306f,0x2bba3074,0xb3c332a5,0x33fdb111,0xa27a3231,0x3389b30d,0x2d5e2f90,0xa216b1aa,0x33feb1a6,0xaed2ae25,0x333db363,
  0xb3652edd,0x2e1ab33a,0xb1aa227a,0x31a6b3fd,0xaf853387,0xb3102d6a,0xb22d33fe,0xb116a216,0x32a9abd3,0xb06f33c2,0x307428a6,0xb2a533ea,
  0x3111b3e9,0x3231a8be,0x330db3c3,0x2f902bba,0xb2e12e31,0x3015b360,0x288db1a1,0x33ebb1af,0xb1e733f5,0xb1662691,0xb33f2f9b,0x2ec6b30a,
  0x2ee82a19,0xb33733da,0xb15833d7,0xb1f42a63,0x33e8b313,0x28d72f7a,0x302525fb,0xb2d833f7,0xb2392d81,0x3107b383,0x3307b3fe,0x2fa6214d,
  0xb35e33ec,0xae3ca874,0x97dbb00f,0x3400b2e5,0xa5c930b7,0xb3f83276,0xb316302a,0x2f6fb2d5,0x32b0aef4,0xb0653335,0xb29e33fd,0xb07f2343,
  0xb1702ccf,0x31dfb3a1,0x3345b124,0xaeaf3221,0xb3fc336c,0xa3a7adf7,0x3332b400,0x2eff997f,0xb0b23304,0xb27a2fb2,0x2b71b102,0x33c8b23d,
  0x2c0e29e8,0xb3bd33dd,0xb0d62a94,0x3260b3d4,0xb0892c1a,0x3297b3bc,0x2aad2842,0xb3d333ee,0xb3b0327e,0x2c6fb0ad,0x3241b035,0xb0fd32ce,
  0xb35933fc,0xae542406,0x3400b392,0x1b112d2f,0xaf5931da,0xb31b3174,0x321db37f,0x3129ad99,0xaf152ac6,0x332cb3d2,0xb1463293,0xb204308e,
  0xb281312e,0x30a8b219,0xab402f4e,0xb3cb331e,0xb3ef3371,0x2829addf,0x2c269c52,0xb3ba3400,0xb37c33f2,0xada52759,0x3179afc8,0xb1d632fe,
  0xacf32953,0x339cb3e3,0xb3fa33cc,0x2500ab28,0xb0942f21,0x3290b32a,0xb3d033fb,0xaade246a,0xb249317d,0x30f3b1d2,0xb2fb337a,0xafd22db1,
  0xb37332f1,0x2dd4aff3,0xb18b3254,0xb1c530e5,0xa96c27bd,0x33e2b3f1,0xb0452fdd,0x32c4b2f7,0xac3e2af7,0x33b7b3cf,0xb0ea3099,0x3250b28c,
  0xadbc2cff,0x3378b39a,0xb1823137,0x31cdb211,0xaf2c2e76,0x3327b352,0xb20d31c9,0x313cb186,0x313c3186,0xb20db1c9,0x2d0b2dc8,0xb398b376,
  0x309e30ee,0xb289b24d,0x2b0f2c4b,0xb3ceb3b5,0x2fe8304a,0xb2f4b2c1,0x27ef2985,0xb3f0b3e1,0x2e822f37,0xb34fb324,0x1ead24ce,0xb3ffb3fa,
  0xb2bdb209,0xb050b141,0xb290b32a,0x30942f21,0xb3b3b34c,0xac57ae8d,0xb0f3b1d2,0x3249317d,0xb400b3ef,0x1d1ba810,0xadd4aff3,0x337332f1,
  0xb39cb3e3,0x2cf32953,0xa500ab28,0x33fa33cc,0xae99b0f8,0x334a3245,0x33ff33b2,0x201f2c63,0x2438a9b6,0x33fc33df,0x332c33d2,0xaf15aac6,
  0x303a2ce7,0x32cb339e,0x30a83219,0xb281b12e,0x32ee31c0,0x2ffe3190,0x28292ddf,0xb3efb371,0x33b0327e,0x2c6f30ad,0xb241b035,0xb0fdb2ce,
  0x335933fc,0xae54a406,0xb400b392,0x1b11ad2f,0x2f5931da,0xb31bb174,0xb21db37f,0x31292d99,0xaaad2842,0xb3d3b3ee,0xa9cfb005,0x33de32eb,
  0x285b305f,0xb3edb2b3,0x2c0ea9e8,0x33bd33dd,0xb170accf,0xb1dfb3a1,0x33453124,0x2eaf3221,0xb3fcb36c,0x23a7adf7,0x33323400,0xaeff997f,
  0xb0b2b304,0x327a2fb2,0x2b713102,0xb3c8b23d,0xb400b2e5,0x17dbb00f,0x2e023264,0xb36ab0d1,0xaf6fb2d5,0x3316302a,0xb11fa8f0,0xb225b3e7,
  0x307f2343,0x329e33fd,0xb3d6b38e,0x2a7cad46,0x33f53342,0xa6c32ebb,0xac87b1e3,0x33ac316b,0x28d7af7a,0x33e83313,0xb2d8b3f7,0x3025a5fb,
  0x33eb31af,0x288d31a1,0x2bebae0e,0x33c03368,0x2ec6330a,0xb33faf9b,0x33fe3235,0x21b1310c,0xb1f4aa63,0xb158b3d7,0x2d5232a2,0xb38bb07a,
  0x33a7333d,0xacab2ed2,0x33f63162,0x262d31eb,0xaa4b301a,0xb3d8b2de,0x2a32326b,0xb3d9b0c7,0xb3f6b26f,0x265fb0c1,0xb3a9b020,0xac9fb2db,
  0x0e48b15d,0x340031f0,0xae1ab33a,0x33652edd,0xaed22e25,0xb33db363,0xb1eb0e48,0xb162b400,0xb2deb3a7,0x301aacab,0xb0c7b3f6,0x326b262d,
  0x30c1aa4b,0x326f33d8,0x32db2a32,0x302033d9,0x31f033f6,0xb15d265f,0x2edd33a9,0xb33aac9f,0xb2acb385,0x306aad76,0x2a19b166,0x33da31e7,
  0x3229a2de,0x311b33fd,0x33133337,0xaf7a2ee8,0x2e3133c5,0xb360aba2,0xb1a128d7,0xb1afb3e8,0xb3f5b015,0xa691b2e1,0xaf9bb3eb,0x330a288d,
  0x3154acc3,0x31f833a3,0x2ef433f8,0xb335a5c9,0x2d8133dc,0xb383aa01,0xb3feb065,0x214db2b0,0xb3ecb107,0x2874b239,0x300fafa6,0x32e53307,
  0x30b7ae3c,0x3276335e,0x302a3400,0xb2d517db,0x312433bd,0xb2212c0e,0xb318b260,0x2f64b0d6,0xb400aeaf,0x997fb345,0x335c20e8,0x2e4833fe,
  0x3102aeff,0x323d3332,0xac7b31fc,0xb3aeb14f,0x2a9433c8,0xb3d4ab71,0xb084b3e6,0x329ba909,0xb2ce2aad,0xb035b3d3,0x33e529cf,0x292233de,
  0x2d2fb241,0x339230fd,0xb14a2fbd,0xb200b301,0x2d993400,0xb37f1b11,0x2084b36f,0x33ff2deb,0xb2ebb21d,0x3005b129,0x30db339f,0xb25c2cdb,
  0xae5fb3e4,0x3357a93b,0xb190303a,0xb1c0b2cb,0x32453258,0xb0f830e0,0x2c63b2ee,0x33b22ffe,0xb3dfae99,0x29b6b34a,0x2ac633ff,0xb3d2a01f,
  0x339ea438,0x2ce733fc,0xb12eb32c,0x3219af15,0x33b8a78b,0x2c3233f2,0x2810b3b3,0x33ef2c57,0xb2c72e6b,0xb040b354,0x29533400,0xb3e31d1b,
  0x3141b133,0x32093215,0xaf21b39c,0x332aacf3,0xae8d32bd,0xb34cb050,0x317d3290,0xb1d23094,0x27bd33fb,0xb3f1249c,0x2fdd3327,0xb2f72f2c,
  0xaaf7b3e2,0x33cfa96c,0xb099b2c4,0x328cb045,0x2cff33b7,0xb39a2c3e,0x31373250,0xb21130ea,0xae76b378,0x3352adbc,0xb1c9b1cd,0x3186b182,
  0xb3ff1ead,0x1de4b3ff,0xb352adbc,0x2e76b378,0x33f1249c,0xa7bd33fb,0x32f72f2c,0xafdd3327,0xb3cfa96c,0x2af7b3e2,0xb28cb045,0x3099b2c4,
  0x339a2c3e,0xacff33b7,0x321130ea,0xb1373250,0x2953b400,0x33e31d1b,0x33ccadd4,0x2b283373,0xaf21339c,0xb32aacf3,0xb3fb2500,0x246ab3fa,
  0x317db290,0x31d23094,0x337a2ade,0xadb133d0,0xb2f130f3,0xaff3b249,0xb254afd2,0x30e5b2fb,0x339e2438,0xace733fc,0xb12e332c,0xb219af15,
  0xb190b03a,0x31c0b2cb,0x3371b0a8,0x2ddf3281,0x2c6332ee,0xb3b22ffe,0xb3f22829,0x2759b3ef,0x2ac6b3ff,0x33d2a01f,0x32932da5,0xb08e337c,
  0xaf0a33f3,0xb32fa727,0x2406b3b0,0x33fcac6f,0x3347b194,0x2ea431bc,0xb1743359,0xb1daae54,0xb3bc2565,0x2c1ab3f9,0x33eeaf59,0x2842331b,
  0x30ad3089,0xb27e3297,0xb2ceaaad,0x3035b3d3,0xb29ba909,0x3084b3e6,0x305f3030,0xb2b332d1,0x259732e8,0xb3f8300a,0x2ccfb3ed,0x33a1a85b,
  0x31b8b381,0x31992d8d,0xb36c31df,0xadf7b170,0xb3f42d3a,0x26f5b390,0x330423a7,0xafb233fc,0x316bb3d6,0x31e32a7c,0xb3832a01,0x2d81b3dc,
  0xb3bf2c87,0x2c02b3ac,0x28743239,0xb3ec3107,0x2b8931b3,0xb3c6319d,0x3276b35e,0x30b72e3c,0x31f8b3a3,0x31542cc3,0xb33525c9,0x2ef4b3f8,
  0x310c2beb,0xb23533c0,0x33abb267,0x2c9330cc,0x307ab3fe,0x32a2a1b1,0xb06aad76,0x32acb385,0xb3a52d52,0x2cb7b38b,0xb11b33fd,0xb229a2de,
  0x94b63273,0xb40030bc,0x3360aba2,0xae3133c5,0xb2de33a7,0xb01aacab,0xb0c733f6,0xb26b262d,0x30c12a4b,0xb26f33d8,0x32dbaa32,0xb02033d9,
  0x31f0b3f6,0x315d265f,0x2eddb3a9,0x333aac9f,0xb1eb8e48,0x3162b400,0xb3872e1a,0x2d6ab365,0xae25ad5e,0x3363b389,0x8e48b15d,0x3400b1f0,
  0xb3a7333d,0xacabaed2,0xb3f63162,0x262db1eb,0x2a4b301a,0xb3d832de,0xaa32326b,0xb3d930c7,0x33f6b26f,0x265f30c1,0x33a9b020,0xac9f32db,
  0x33c0b368,0x2beb2e0e,0x30cc94b6,0xb2673400,0x21b1b10c,0x33feb235,0x3385b3ab,0x2d762c93,0xb38b307a,0x2d52b2a2,0xa2deb06a,0x33fdb2ac,
  0xb0bc33a5,0xb2732cb7,0xb3c5311b,0x2ba2b229,0x26c32ebb,0xb3f53342,0xb3ac316b,0x2c87b1e3,0x336ab0d1,0xae023264,0xb19d33bf,0xb1b32c02,
  0x3225b3e7,0x311fa8f0,0x2cc32b89,0xb3a333c6,0xaa7cad46,0x33d6b38e,0x33dcb1f8,0xaa013154,0xb3fe3318,0x20e8af64,0x3381b3f8,0x2d8d2597,
  0xb14f335c,0xb1fc2e48,0x2d3ab199,0x3390b1b8,0x29092c7b,0xb3e633ae,0xb03026f5,0x32d1b3f4,0x32e8b084,0xb00a329b,0xb3ed32b3,0x285bb05f,
  0x29cfb005,0x33deb2eb,0xb05a325c,0xb2b630db,0xafbd2922,0x3301b3e5,0x27272b59,0xb3f333c9,0xb36f3200,0x2debb14a,0x31bcaf0a,0xb194332f,
  0xb39f33ff,0xacdba084,0x33f9b347,0xa5652ea4,0x3394b2ba,0xad233055,0xa438a9b6,0x33fcb3df,0x33e4b3f9,0x293b2533,0xb03a2ce7,0x32cbb39e,
  0x3258b357,0x30e0ae5f,0xb2ee31c0,0x2ffeb190,0x2e99b0f8,0x334ab245,0xb3ff33b2,0x201fac63,0xaf4230a3,0xb3213285,0x3133b040,0xb21532c7,
  0xa99e2d17,0xb3e03396,0x32bdb209,0xb0503141,0x278b1f76,0xb3f233ff,0x33b3b34c,0xac572e8d,0x2e6bac32,0xb35433b8,0x3400b3ef,0x1d1b2810,
  0xb289324d,0x309eb0ee,0xb3ce33b5,0x2b0fac4b,0xb2f432c1,0x2fe8b04a,0xb3f033e1,0x27efa985,0xb34f3324,0x2e82af37,0xb3ff33fa,0x1eada4ce,
  0xb3983376,0x2d0badc8,0xb3fb33ff,0xa49c1de4,0x351c35f6,0xac93a617,0xb8a3b93c,0x308d2a16,0x32f43448,0xb160afa5,0xb6a4b7fe,0x353a3389,
  0x2fa53160,0xb448b2f4,0xb389b53a,0x37fe36a4,0x26172c93,0xb5f6b51c,0xaa16b08d,0x393c38a3,0x34c3358c,0xac47a5b2,0xb85fb8f3,0x304229b1,
  0x327e33fd,0xb106af26,0xb63cb785,0x34e7330f,0x2f263106,0xb3fdb27e,0xb30fb4e7,0x3785363c,0x25b22c47,0xb58cb4c3,0xa9b1b042,0x38f3385f,
  0x346a3523,0xabf6a54d,0xb81ab8a8,0x2fef294d,0x3209336b,0xb0acaea7,0xb5d4b70a,0x34933294,0x2ea730ac,0xb36bb209,0xb294b493,0x370a35d4,
  0x254d2bf6,0xb523b46a,0xa94dafef,0x38a8381a,0x341334bc,0xab5fa4e9,0xb7a6b85a,0x2f5928e8,0x319432da,0xb052ae28,0xb56ab68d,0x343e3219,
  0x2e283052,0xb2dab194,0xb219b43e,0x368d356a,0x24e92b5f,0xb4bcb413,0xa8e8af59,0x385a37a6,0x33783456,0xaac8a484,0xb715b80a,0x2ec32884,
  0x3120324a,0xaff2ada9,0xb4ffb60e,0x33d3319e,0x2da92ff2,0xb24ab120,0xb19eb3d3,0x360e34ff,0x24842ac8,0xb456b378,0xa884aec3,0x380a3715,
  0x32cd33e3,0xaa31a420,0xb682b76f,0x2e2d281f,0x30ac31bb,0xaf3fad2a,0xb493b58d,0x33283122,0x2d2a2f3f,0xb1bbb0ac,0xb122b328,0x358d3493,
  0x24202a31,0xb3e3b2cd,0xa81fae2d,0x376f3682,0x3223331c,0xa999a376,0xb5ebb6c6,0x2d972776,0x3039312d,0xae8dacac,0xb426b50b,0x327c30a6,
  0x2cac2e8d,0xb12db039,0xb0a6b27c,0x350b3426,0x23762999,0xb31cb223,0xa776ad97,0x36c635eb,0x317a3257,0xa902a2ad,0xb552b61a,0x2d0026ad,
  0x2f8c309f,0xaddcac2e,0xb371b487,0x31cf3029,0x2c2e2ddc,0xb09faf8c,0xb029b1cf,0x34873371,0x22ad2902,0xb257b17a,0xa6adad00,0x361a3552,
  0x30d23194,0xa86ba1e4,0xb4b7b56a,0x2c6a25e4,0x2ea73012,0xad2aab5f,0xb294b402,0x31222f59,0x2b5f2d2a,0xb012aea7,0xaf59b122,0x34023294,
  0x21e4286b,0xb194b0d2,0xa5e4ac6a,0x356a34b7,0x302c30d2,0xa7a9a11b,0xb41ab4b7,0x2ba7251b,0x2dc22f0c,0xac79aa63,0xb1b6b2f7,0x30742e5f,
  0x2a632c79,0xaf0cadc2,0xae5fb074,0x32f731b6,0x211b27a9,0xb0d2b02c,0xa51baba7,0x34b7341a,0x2f0c3012,0xa67ba052,0xb2f7b402,0x2a7a2452,
  0x2cde2df5,0xab91a967,0xb0d7b1e8,0x2f8b2d65,0x29672b91,0xadf5acde,0xad65af8b,0x31e830d7,0x2052267b,0xb012af0c,0xa452aa7a,0x340232f7,
  0x2dc22ea7,0xa54d9f12,0xb1b6b294,0x294d2311,0x2bf62cde,0xaa31a86b,0xafefb0d7,0x2e2d2c6a,0x286b2a31,0xacdeabf6,0xac6aae2d,0x30d72fef,
  0x1f12254d,0xaea7adc2,0xa311a94d,0x329431b6,0x2c792d2a,0xa4209d7f,0xb074b122,0x281f217f,0x2a312b91,0xa8d0a6e0,0xae2daf8b,0x2cce2ade,
  0x26e028d0,0xab91aa31,0xaadeacce,0x2f8b2e2d,0x1d7f2420,0xad2aac79,0xa17fa81f,0x31223074,0x2a632b5f,0xa1e49bdb,0xae5faf59,0x25e41fdb,
  0x286b2967,0xa6e0a4e9,0xac6aad65,0x2ade28e8,0x24e926e0,0xa967a86b,0xa8e8aade,0x2d652c6a,0x1bdb21e4,0xab5faa63,0x9fdba5e4,0x2f592e5f,
  0x27a9286b,0x9f1298b6,0xaba7ac6a,0x23111cb6,0x254d267b,0xa420a1e4,0xa94daa7a,0x281f25e4,0x21e42420,0xa67ba54d,0xa5e4a81f,0x2a7a294d,
  0x18b61f12,0xa86ba7a9,0x9cb6a311,0x2c6a2ba7,0x211b21e4,0x98b69248,0xa51ba5e4,0x1cb61648,0x1f122052,0x9d7f9bdb,0xa311a452,0x217f1fdb,
  0x1bdb1d7f,0xa0529f12,0x9fdba17f,0x24522311,0x124818b6,0xa1e4a11b,0x96489cb6,0x25e4251b,0xa11ba1e4,0x18b61248,0x251b25e4,0x9cb69648,
  0x9f12a052,0x1d7f1bdb,0x23112452,0xa17f9fdb,0x9bdb9d7f,0x20521f12,0x1fdb217f,0xa452a311,0x924898b6,0x21e4211b,0x16481cb6,0xa5e4a51b,
  0xa7a9a86b,0x1f1218b6,0x2ba72c6a,0xa3119cb6,0xa54da67b,0x242021e4,0x294d2a7a,0xa81fa5e4,0xa1e4a420,0x267b254d,0x25e4281f,0xaa7aa94d,
  0x98b69f12,0x286b27a9,0x1cb62311,0xac6aaba7,0xaa63ab5f,0x21e41bdb,0x2e5f2f59,0xa5e49fdb,0xa86ba967,0x26e024e9,0x2c6a2d65,0xaadea8e8,
  0xa4e9a6e0,0x2967286b,0x28e82ade,0xad65ac6a,0x9bdba1e4,0x2b5f2a63,0x1fdb25e4,0xaf59ae5f,0xac79ad2a,0x24201d7f,0x30743122,0xa81fa17f,
  0xaa31ab91,0x28d026e0,0x2e2d2f8b,0xacceaade,0xa6e0a8d0,0x2b912a31,0x2ade2cce,0xaf8bae2d,0x9d7fa420,0x2d2a2c79,0x217f281f,0xb122b074,
  0xadc2aea7,0x254d1f12,0x31b63294,0xa94da311,0xabf6acde,0x2a31286b,0x2fef30d7,0xae2dac6a,0xa86baa31,0x2cde2bf6,0x2c6a2e2d,0xb0d7afef,
  0x9f12a54d,0x2ea72dc2,0x2311294d,0xb294b1b6,0xaf0cb012,0x267b2052,0x32f73402,0xaa7aa452,0xacdeadf5,0x2b912967,0x30d731e8,0xaf8bad65,
  0xa967ab91,0x2df52cde,0x2d652f8b,0xb1e8b0d7,0xa052a67b,0x30122f0c,0x24522a7a,0xb402b2f7,0xb02cb0d2,0x27a9211b,0x341a34b7,0xaba7a51b,
  0xadc2af0c,0x2c792a63,0x31b632f7,0xb074ae5f,0xaa63ac79,0x2f0c2dc2,0x2e5f3074,0xb2f7b1b6,0xa11ba7a9,0x30d2302c,0x251b2ba7,0xb4b7b41a,
  0xb0d2b194,0x286b21e4,0x34b7356a,0xac6aa5e4,0xaea7b012,0x2d2a2b5f,0x32943402,0xb122af59,0xab5fad2a,0x30122ea7,0x2f593122,0xb402b294,
  0xa1e4a86b,0x319430d2,0x25e42c6a,0xb56ab4b7,0xb17ab257,0x290222ad,0x3552361a,0xad00a6ad,0xaf8cb09f,0x2ddc2c2e,0x33713487,0xb1cfb029,
  0xac2eaddc,0x309f2f8c,0x302931cf,0xb487b371,0xa2ada902,0x3257317a,0x26ad2d00,0xb61ab552,0xb223b31c,0x29992376,0x35eb36c6,0xad97a776,
  0xb039b12d,0x2e8d2cac,0x3426350b,0xb27cb0a6,0xacacae8d,0x312d3039,0x30a6327c,0xb50bb426,0xa376a999,0x331c3223,0x27762d97,0xb6c6b5eb,
  0xb2cdb3e3,0x2a312420,0x3682376f,0xae2da81f,0xb0acb1bb,0x2f3f2d2a,0x3493358d,0xb328b122,0xad2aaf3f,0x31bb30ac,0x31223328,0xb58db493,
  0xa420aa31,0x33e332cd,0x281f2e2d,0xb76fb682,0xb378b456,0x2ac82484,0x3715380a,0xaec3a884,0xb120b24a,0x2ff22da9,0x34ff360e,0xb3d3b19e,
  0xada9aff2,0x324a3120,0x319e33d3,0xb60eb4ff,0xa484aac8,0x34563378,0x28842ec3,0xb80ab715,0xb413b4bc,0x2b5f24e9,0x37a6385a,0xaf59a8e8,
  0xb194b2da,0x30522e28,0x356a368d,0xb43eb219,0xae28b052,0x32da3194,0x3219343e,0xb68db56a,0xa4e9ab5f,0x34bc3413,0x28e82f59,0xb85ab7a6,
  0xb46ab523,0x2bf6254d,0x381a38a8,0xafefa94d,0xb209b36b,0x30ac2ea7,0x35d4370a,0xb493b294,0xaea7b0ac,0x336b3209,0x32943493,0xb70ab5d4,
  0xa54dabf6,0x3523346a,0x294d2fef,0xb8a8b81a,0xb4c3b58c,0x2c4725b2,0x385f38f3,0xb042a9b1,0xb27eb3fd,0x31062f26,0x363c3785,0xb4e7b30f,
  0xaf26b106,0x33fd327e,0x330f34e7,0xb785b63c,0xa5b2ac47,0x358c34c3,0x29b13042,0xb8f3b85f,0xb51cb5f6,0x2c932617,0x38a3393c,0xb08daa16,
  0xb2f4b448,0x31602fa5,0x36a437fe,0xb53ab389,0xafa5b160,0x344832f4,0x3389353a,0xb7feb6a4,0xa617ac93,0x35f6351c,0x2a16308d,0xb93cb8a3,
};
__device__ __align__(128) const uint32_t c_img[2560] = {
  0x326d31ed,0x333b32dd,0x33c33388,0x33fe33ea,0x33c331ed,0x31ed33c3,0xa8b22d64,0xb33bb0c4,0x33ea31ed,0xad64301d,0xb2ddb388,0x315fa8b2,
  0x32dd31ed,0xb3feabc6,0x326dad64,0xad64326d,0x30c431ed,0xaed7b2dd,0x2bc63388,0xa248b3ea,0x2bc631ed,0x315fb3c3,0xb3ea2d64,0x2ed730c4,
  0xa8b231ed,0x3388b01d,0x301db388,0xb1ed28b2,0xb01d31ed,0x22482bc6,0x30c4ad64,0x3388b26d,0x33ea33fe,0x338833c3,0x32dd333b,0x31ed326d,
  0xb2ddb3fe,0xa248b01d,0x326d2ed7,0x338833ea,0x30c433fe,0xb33babc6,0xabc6b33b,0x33fe30c4,0xabc6b3fe,0x31ed32dd,0xb3eaaed7,0x333ba8b2,
  0xa8b233fe,0x2d64b3c3,0xb01d333b,0x315fb26d,0x301db3fe,0xb3fe301d,0x30c42ed7,0x2d64b3ea,0xb26d33fe,0x2ed72bc6,0x33c3b33b,0xa248b0c4,
  0x33c3b3fe,0x315fb2dd,0x28b2aed7,0xaed728b2,0xb0c4b15f,0xaed7b01d,0xabc6ad64,0xa248a8b2,0xabc6b15f,0x315f2bc6,0x33ea3388,0x2ed7326d,
  0x28b2b15f,0x338832dd,0xb01d2d64,0xb1edb3ea,0x301db15f,0x224833c3,0xb0c4b388,0x338830c4,0x326db15f,0xb33b301d,0x33c3ad64,0xb3fe28b2,
  0x33c3b15f,0xb1edabc6,0xa8b23388,0x333bb26d,0x33eab15f,0x2d64b2dd,0xb2dd2d64,0xb15f33ea,0x32ddb15f,0x33feb3c3,0x326db388,0x2d64b0c4,
  0x28b22248,0x2d642bc6,0x301d2ed7,0x315f30c4,0xb01da248,0xb3feb2dd,0xb0c4b33b,0x2d64a8b2,0x326d2248,0x2ed733c3,0xb3c3aed7,0xa248b26d,
  0xb3c3a248,0x315fb01d,0xa8b2333b,0xaed7b3ea,0x33ea2248,0xb388abc6,0x32dd2ed7,0xb1edb0c4,0xb2dda248,0x224832dd,0x326db33b,0xb38828b2,
  0x30c42248,0x333bb3c3,0xabc6aed7,0xb3fe326d,0xabc6a248,0xb1ed301d,0xb3ea333b,0xb33b33ea,0xb26d31ed,0xb33b32dd,0xb3c33388,0xb3fe33ea,
  0xb3c331ed,0xb1ed33c3,0x28b22d64,0x333bb0c4,0xb3ea31ed,0x2d64301d,0x32ddb388,0xb15fa8b2,0xb2dd31ed,0x33feabc6,0xb26dad64,0x2d64326d,
  0xb0c431ed,0x2ed7b2dd,0xabc63388,0x2248b3ea,0xabc631ed,0xb15fb3c3,0x33ea2d64,0xaed730c4,0x28b231ed,0xb388b01d,0xb01db388,0x31ed28b2,
  0x301d31ed,0xa2482bc6,0xb0c4ad64,0xb388b26d,0xb3ea33fe,0xb38833c3,0xb2dd333b,0xb1ed326d,0x32ddb3fe,0x2248b01d,0xb26d2ed7,0xb38833ea,
  0xb0c433fe,0x333babc6,0x2bc6b33b,0xb3fe30c4,0x2bc6b3fe,0xb1ed32dd,0x33eaaed7,0xb33ba8b2,0x28b233fe,0xad64b3c3,0x301d333b,0xb15fb26d,
  0xb01db3fe,0x33fe301d,0xb0c42ed7,0xad64b3ea,0x326d33fe,0xaed72bc6,0xb3c3b33b,0x2248b0c4,0xb3c3b3fe,0xb15fb2dd,0xa8b2aed7,0x2ed728b2,
  0x30c4b15f,0x2ed7b01d,0x2bc6ad64,0x2248a8b2,0x2bc6b15f,0xb15f2bc6,0xb3ea3388,0xaed7326d,0xa8b2b15f,0xb38832dd,0x301d2d64,0x31edb3ea,
  0xb01db15f,0xa24833c3,0x30c4b388,0xb38830c4,0xb26db15f,0x333b301d,0xb3c3ad64,0x33fe28b2,0xb3c3b15f,0x31edabc6,0x28b23388,0xb33bb26d,
  0xb3eab15f,0xad64b2dd,0x32dd2d64,0x315f33ea,0xb2ddb15f,0xb3feb3c3,0xb26db388,0xad64b0c4,0xa8b22248,0xad642bc6,0xb01d2ed7,0xb15f30c4,
  0x301da248,0x33feb2dd,0x30c4b33b,0xad64a8b2,0xb26d2248,0xaed733c3,0x33c3aed7,0x2248b26d,0x33c3a248,0xb15fb01d,0x28b2333b,0x2ed7b3ea,
  0xb3ea2248,0x3388abc6,0xb2dd2ed7,0x31edb0c4,0x32dda248,0xa24832dd,0xb26db33b,0x338828b2,0xb0c42248,0xb33bb3c3,0x2bc6aed7,0x33fe326d,
  0x2bc6a248,0x31ed301d,0x33ea333b,0x333b33ea,0x30c4315f,0x2ed7301d,0x2bc62d64,0x224828b2,0x2bc6315f,0xb15fabc6,0xb3eab388,0xaed7b26d,
  0xa8b2315f,0xb388b2dd,0x301dad64,0x31ed33ea,0xb01d315f,0xa248b3c3,0x30c43388,0xb388b0c4,0xb26d315f,0x333bb01d,0xb3c32d64,0x33fea8b2,
  0xb3c3315f,0x31ed2bc6,0x28b2b388,0xb33b326d,0xb3ea315f,0xad6432dd,0x32ddad64,0x315fb3ea,0xb2dd315f,0xb3fe33c3,0xb26d3388,0xad6430c4,
  0xa8b2a248,0xad64abc6,0xb01daed7,0xb15fb0c4,0x301d2248,0x33fe32dd,0x30c4333b,0xad6428b2,0xb26da248,0xaed7b3c3,0x33c32ed7,0x2248326d,
  0x33c32248,0xb15f301d,0x28b2b33b,0x2ed733ea,0xb3eaa248,0x33882bc6,0xb2ddaed7,0x31ed30c4,0x32dd2248,0xa248b2dd,0xb26d333b,0x3388a8b2,
  0xb0c4a248,0xb33b33c3,0x2bc62ed7,0x33feb26d,0x2bc62248,0x31edb01d,0x33eab33b,0x333bb3ea,0x326d31ed,0x333b32dd,0x33c33388,0x33fe33ea,
  0x33c331ed,0x31ed33c3,0xa8b22d64,0xb33bb0c4,0x33ea31ed,0xad64301d,0xb2ddb388,0x315fa8b2,0x32dd31ed,0xb3feabc6,0x326dad64,0xad64326d,
  0x30c431ed,0xaed7b2dd,0x2bc63388,0xa248b3ea,0x2bc631ed,0x315fb3c3,0xb3ea2d64,0x2ed730c4,0xa8b231ed,0x3388b01d,0x301db388,0xb1ed28b2,
  0xb01d31ed,0x22482bc6,0x30c4ad64,0x3388b26d,0x33ea33fe,0x338833c3,0x32dd333b,0x31ed326d,0xb2ddb3fe,0xa248b01d,0x326d2ed7,0x338833ea,
  0x30c433fe,0xb33babc6,0xabc6b33b,0x33fe30c4,0xabc6b3fe,0x31ed32dd,0xb3eaaed7,0x333ba8b2,0xa8b233fe,0x2d64b3c3,0xb01d333b,0x315fb26d,
  0x301db3fe,0xb3fe301d,0x30c42ed7,0x2d64b3ea,0xb26d33fe,0x2ed72bc6,0x33c3b33b,0xa248b0c4,0x33c3b3fe,0x315fb2dd,0x28b2aed7,0xaed728b2,
  0xb0c4315f,0xaed7301d,0xabc62d64,0xa24828b2,0xabc6315f,0x315fabc6,0x33eab388,0x2ed7b26d,0x28b2315f,0x3388b2dd,0xb01dad64,0xb1ed33ea,
  0x301d315f,0x2248b3c3,0xb0c43388,0x3388b0c4,0x326d315f,0xb33bb01d,0x33c32d64,0xb3fea8b2,0x33c3315f,0xb1ed2bc6,0xa8b2b388,0x333b326d,
  0x33ea315f,0x2d6432dd,0xb2ddad64,0xb15fb3ea,0x32dd315f,0x33fe33c3,0x326d3388,0x2d6430c4,0x28b2a248,0x2d64abc6,0x301daed7,0x315fb0c4,
  0xb01d2248,0xb3fe32dd,0xb0c4333b,0x2d6428b2,0x326da248,0x2ed7b3c3,0xb3c32ed7,0xa248326d,0xb3c32248,0x315f301d,0xa8b2b33b,0xaed733ea,
  0x33eaa248,0xb3882bc6,0x32ddaed7,0xb1ed30c4,0xb2dd2248,0x2248b2dd,0x326d333b,0xb388a8b2,0x30c4a248,0x333b33c3,0xabc62ed7,0xb3feb26d,
  0xabc62248,0xb1edb01d,0xb3eab33b,0xb33bb3ea,0xb26d31ed,0xb33b32dd,0xb3c33388,0xb3fe33ea,0xb3c331ed,0xb1ed33c3,0x28b22d64,0x333bb0c4,
  0xb3ea31ed,0x2d64301d,0x32ddb388,0xb15fa8b2,0xb2dd31ed,0x33feabc6,0xb26dad64,0x2d64326d,0xb0c431ed,0x2ed7b2dd,0xabc63388,0x2248b3ea,
  0xabc631ed,0xb15fb3c3,0x33ea2d64,0xaed730c4,0x28b231ed,0xb388b01d,0xb01db388,0x31ed28b2,0x301d31ed,0xa2482bc6,0xb0c4ad64,0xb388b26d,
  0xb3ea33fe,0xb38833c3,0xb2dd333b,0xb1ed326d,0x32ddb3fe,0x2248b01d,0xb26d2ed7,0xb38833ea,0xb0c433fe,0x333babc6,0x2bc6b33b,0xb3fe30c4,
  0x2bc6b3fe,0xb1ed32dd,0x33eaaed7,0xb33ba8b2,0x28b233fe,0xad64b3c3,0x301d333b,0xb15fb26d,0xb01db3fe,0x33fe301d,0xb0c42ed7,0xad64b3ea,
  0x326d33fe,0xaed72bc6,0xb3c3b33b,0x2248b0c4,0xb3c3b3fe,0xb15fb2dd,0xa8b2aed7,0x2ed728b2,0x29ed29ed,0x29ed29ed,0x29ed29ed,0x29ed29ed,
  0x2bc32a6d,0x2add2bea,0x23c628c4,0xa81da0b2,0x2bc32add,0xa3c6281d,0xabc3aadd,0x23c6a81d,0x29ed2b3b,0xabfea564,0x295fa6d7,0x1a482b88,
  0x25642b88,0xa564ab88,0x25642b88,0xa564ab88,0xa0b22bc3,0x2a6daadd,0xabea23c6,0x28c4281d,0xa8c42bea,0x2a6da0b2,0x28c4abea,0xaa6d20b2,
  0xab3b2bfe,0xa564295f,0x26d79a48,0x2b88a9ed,0x29ed29ed,0x29ed29ed,0x29ed29ed,0x29ed29ed,0xabc3aa6d,0xaaddabea,0xa3c6a8c4,0x281d20b2,
  0x2bc32add,0xa3c6281d,0xabc3aadd,0x23c6a81d,0xa9edab3b,0x2bfe2564,0xa95f26d7,0x9a48ab88,0x25642b88,0xa564ab88,0x25642b88,0xa564ab88,
  0x20b2abc3,0xaa6d2add,0x2beaa3c6,0xa8c4a81d,0xa8c42bea,0x2a6da0b2,0x28c4abea,0xaa6d20b2,0x2b3babfe,0x2564a95f,0xa6d71a48,0xab8829ed,
  0x295f295f,0x295f295f,0x295f295f,0x295f295f,0x23c628c4,0xa81da0b2,0xabc3aa6d,0xaaddabea,0xa3c6281d,0xabc3aadd,0x23c6a81d,0x2bc32add,
  0xa95f26d7,0x9a48ab88,0x29ed2b3b,0xabfea564,0xab882564,0x2b88a564,0xab882564,0x2b88a564,0xabea23c6,0x28c4281d,0x20b2abc3,0xaa6d2add,
  0xaa6d20b2,0xa8c42bea,0x2a6da0b2,0x28c4abea,0xa6d71a48,0xab8829ed,0xab3b2bfe,0xa564295f,0x295f295f,0x295f295f,0x295f295f,0x295f295f,
  0xa3c6a8c4,0x281d20b2,0x2bc32a6d,0x2add2bea,0xa3c6281d,0xabc3aadd,0x23c6a81d,0x2bc32add,0x295fa6d7,0x1a482b88,0xa9edab3b,0x2bfe2564,
  0xab882564,0x2b88a564,0xab882564,0x2b88a564,0x2beaa3c6,0xa8c4a81d,0xa0b22bc3,0x2a6daadd,0xaa6d20b2,0xa8c42bea,0x2a6da0b2,0x28c4abea,
  0x26d79a48,0x2b88a9ed,0x2b3babfe,0x2564a95f,0xabfe2bfe,0xabfe2bfe,0xabfe2bfe,0xabfe2bfe,0xaadd2bea,0xa3c628c4,0x281da0b2,0x2bc3aa6d,
  0xa81d2bc3,0x2adda3c6,0x281dabc3,0xaadd23c6,0x9a482b88,0x29edab3b,0xabfe2564,0x295f26d7,0x26d72b3b,0xa6d7ab3b,0x26d72b3b,0xa6d7ab3b,
  0x2a6d2add,0xabeaa3c6,0x28c4a81d,0x20b22bc3,0x2bea2a6d,0xa0b228c4,0xabeaaa6d,0x20b2a8c4,0x2b8829ed,0x2b3b2bfe,0x2564295f,0xa6d79a48,
  0xabfe2bfe,0xabfe2bfe,0xabfe2bfe,0xabfe2bfe,0x2addabea,0x23c6a8c4,0xa81d20b2,0xabc32a6d,0xa81d2bc3,0x2adda3c6,0x281dabc3,0xaadd23c6,
  0x1a48ab88,0xa9ed2b3b,0x2bfea564,0xa95fa6d7,0x26d72b3b,0xa6d7ab3b,0x26d72b3b,0xa6d7ab3b,0xaa6daadd,0x2bea23c6,0xa8c4281d,0xa0b2abc3,
  0x2bea2a6d,0xa0b228c4,0xabeaaa6d,0x20b2a8c4,0xab88a9ed,0xab3babfe,0xa564a95f,0x26d71a48,0x1a489a48,0x1a489a48,0x1a489a48,0x1a489a48,
  0x281da0b2,0x2bc3aa6d,0x2addabea,0x23c6a8c4,0x2adda3c6,0x281dabc3,0xaadd23c6,0xa81d2bc3,0x2bfea564,0xa95fa6d7,0x9a482b88,0x29edab3b,
  0x2b3ba6d7,0xab3b26d7,0x2b3ba6d7,0xab3b26d7,0x28c4a81d,0x20b22bc3,0xaa6daadd,0x2bea23c6,0x20b2a8c4,0x2bea2a6d,0xa0b228c4,0xabeaaa6d,
  0xa564a95f,0x26d71a48,0x2b8829ed,0x2b3b2bfe,0x1a489a48,0x1a489a48,0x1a489a48,0x1a489a48,0xa81d20b2,0xabc32a6d,0xaadd2bea,0xa3c628c4,
  0x2adda3c6,0x281dabc3,0xaadd23c6,0xa81d2bc3,0xabfe2564,0x295f26d7,0x1a48ab88,0xa9ed2b3b,0x2b3ba6d7,0xab3b26d7,0x2b3ba6d7,0xab3b26d7,
  0xa8c4281d,0xa0b2abc3,0x2a6d2add,0xabeaa3c6,0x20b2a8c4,0x2bea2a6d,0xa0b228c4,0xabeaaa6d,0x2564295f,0xa6d79a48,0xab88a9ed,0xab3babfe,
  0xa95fa95f,0xa95fa95f,0xa95fa95f,0xa95fa95f,0xa3c6a8c4,0x281d20b2,0x2bc32a6d,0x2add2bea,0x23c6a81d,0x2bc32add,0xa3c6281d,0xabc3aadd,
  0x295fa6d7,0x1a482b88,0xa9edab3b,0x2bfe2564,0x2b88a564,0xab882564,0x2b88a564,0xab882564,0x2beaa3c6,0xa8c4a81d,0xa0b22bc3,0x2a6daadd,
  0x2a6da0b2,0x28c4abea,0xaa6d20b2,0xa8c42bea,0x26d79a48,0x2b88a9ed,0x2b3babfe,0x2564a95f,0xa95fa95f,0xa95fa95f,0xa95fa95f,0xa95fa95f,
  0x23c628c4,0xa81da0b2,0xabc3aa6d,0xaaddabea,0x23c6a81d,0x2bc32add,0xa3c6281d,0xabc3aadd,0xa95f26d7,0x9a48ab88,0x29ed2b3b,0xabfea564,
  0x2b88a564,0xab882564,0x2b88a564,0xab882564,0xabea23c6,0x28c4281d,0x20b2abc3,0xaa6d2add,0x2a6da0b2,0x28c4abea,0xaa6d20b2,0xa8c42bea,
  0xa6d71a48,0xab8829ed,0xab3b2bfe,0xa564295f,0x29ed29ed,0x29ed29ed,0x29ed29ed,0x29ed29ed,0x2bc32a6d,0x2add2bea,0x23c628c4,0xa81da0b2,
  0x2bc32add,0xa3c6281d,0xabc3aadd,0x23c6a81d,0x29ed2b3b,0xabfea564,0x295fa6d7,0x1a482b88,0x25642b88,0xa564ab88,0x25642b88,0xa564ab88,
  0xa0b22bc3,0x2a6daadd,0xabea23c6,0x28c4281d,0xa8c42bea,0x2a6da0b2,0x28c4abea,0xaa6d20b2,0xab3b2bfe,0xa564295f,0x26d79a48,0x2b88a9ed,
  0x29ed29ed,0x29ed29ed,0x29ed29ed,0x29ed29ed,0xabc3aa6d,0xaaddabea,0xa3c6a8c4,0x281d20b2,0x2bc32add,0xa3c6281d,0xabc3aadd,0x23c6a81d,
  0xa9edab3b,0x2bfe2564,0xa95f26d7,0x9a48ab88,0x25642b88,0xa564ab88,0x25642b88,0xa564ab88,0x20b2abc3,0xaa6d2add,0x2beaa3c6,0xa8c4a81d,
  0xa8c42bea,0x2a6da0b2,0x28c4abea,0xaa6d20b2,0x2b3babfe,0x2564a95f,0xa6d71a48,0xab8829ed,0x9a481a48,0x9a481a48,0x9a481a48,0x9a481a48,
  0xa81d20b2,0xabc32a6d,0xaadd2bea,0xa3c628c4,0xaadd23c6,0xa81d2bc3,0x2adda3c6,0x281dabc3,0xabfe2564,0x295f26d7,0x1a48ab88,0xa9ed2b3b,
  0xab3b26d7,0x2b3ba6d7,0xab3b26d7,0x2b3ba6d7,0xa8c4281d,0xa0b2abc3,0x2a6d2add,0xabeaa3c6,0xa0b228c4,0xabeaaa6d,0x20b2a8c4,0x2bea2a6d,
  0x2564295f,0xa6d79a48,0xab88a9ed,0xab3babfe,0x9a481a48,0x9a481a48,0x9a481a48,0x9a481a48,0x281da0b2,0x2bc3aa6d,0x2addabea,0x23c6a8c4,
  0xaadd23c6,0xa81d2bc3,0x2adda3c6,0x281dabc3,0x2bfea564,0xa95fa6d7,0x9a482b88,0x29edab3b,0xab3b26d7,0x2b3ba6d7,0xab3b26d7,0x2b3ba6d7,
  0x28c4a81d,0x20b22bc3,0xaa6daadd,0x2bea23c6,0xa0b228c4,0xabeaaa6d,0x20b2a8c4,0x2bea2a6d,0xa564a95f,0x26d71a48,0x2b8829ed,0x2b3b2bfe,
  0xabfe2bfe,0xabfe2bfe,0xabfe2bfe,0xabfe2bfe,0xaadd2bea,0xa3c628c4,0x281da0b2,0x2bc3aa6d,0xa81d2bc3,0x2adda3c6,0x281dabc3,0xaadd23c6,
  0x9a482b88,0x29edab3b,0xabfe2564,0x295f26d7,0x26d72b3b,0xa6d7ab3b,0x26d72b3b,0xa6d7ab3b,0x2a6d2add,0xabeaa3c6,0x28c4a81d,0x20b22bc3,
  0x2bea2a6d,0xa0b228c4,0xabeaaa6d,0x20b2a8c4,0x2b8829ed,0x2b3b2bfe,0x2564295f,0xa6d79a48,0xabfe2bfe,0xabfe2bfe,0xabfe2bfe,0xabfe2bfe,
  0x2addabea,0x23c6a8c4,0xa81d20b2,0xabc32a6d,0xa81d2bc3,0x2adda3c6,0x281dabc3,0xaadd23c6,0x1a48ab88,0xa9ed2b3b,0x2bfea564,0xa95fa6d7,
  0x26d72b3b,0xa6d7ab3b,0x26d72b3b,0xa6d7ab3b,0xaa6daadd,0x2bea23c6,0xa8c4281d,0xa0b2abc3,0x2bea2a6d,0xa0b228c4,0xabeaaa6d,0x20b2a8c4,
  0xab88a9ed,0xab3babfe,0xa564a95f,0x26d71a48,0x3bfb3bff,0x3be53bf2,0x3bbf3bd4,0x3b873ba5,0x3bd03bfb,0x3b013b7c,0x399d3a60,0x378538bc,
  0x3a543bcf,0x2884374e,0xb9f8b648,0xbbe9bbab,0x398b3bb7,0xb4db3340,0xbbdcb9fc,0xb911bb85,0x35173b52,0xbbc9b7c8,0xb074ba9b,0x3bfe391b,
  0x319e3b27,0xbbf3b979,0x363cb80a,0x3a2d3bc5,0xb4323a8c,0xb6a4bbf9,0x3b3539b8,0xbbc3ae91,0xb66b3a50,0xad65bbe4,0x38653b90,0xbb0db966,
  0xac6aa5e4,0xb122af59,0xb402b294,0xb56ab4b7,0xb2deac9c,0xb7bdb5a5,0xb9b3b8d6,0xbb10ba73,0xb8e5b2f7,0xbbffbb1e,0xb954bb5c,0x30beb493,
  0xb9c5b43e,0xbb9fbbcb,0xb201b94f,0x3a313576,0xbb96b676,0xb359bafe,0x3bec3884,0x2a163a29,0xbbe0b72c,0x2f27b9d6,0x3b5e3ae8,0xb91633a2,
  0xbbb8b899,0x3b47ad33,0xb6f43999,0xb3babbf5,0xbb54b8ea,0x3bf9313b,0xbab0353a,0x3790b9e7,0x3b3f3b65,0x3ae83b16,0x3a813ab6,0x3a0d3a49,
  0x3263356a,0xad972b43,0xb5dfb359,0xb8eeb7f3,0xb825baa9,0x353aaec3,0x3b7c3994,0x3af43bfa,0x360eb0be,0x3bf43a64,0x388e3b47,0xb7372c6a,
  0xa9b139aa,0xbbedba25,0x3340b889,0x3b983afb,0xbaa2aa16,0xb4cfbb8e,0x3c0038ad,0xb44b38e5,0x38bcb874,0x2ba73bac,0xb979bb59,0x3bf03742,
  0x3c0033ba,0xbb043402,0x3855b974,0xacce3b96,0xb6c6b61a,0xb80ab76f,0xb8a8b85a,0xb93cb8f3,0xbbd7bb87,0xbbf8bbfd,0xbb71bbc9,0xba4dbaf1,
  0x3ad8386f,0x3b903bf5,0x35a539bc,0xb7e8ad00,0x3b683be9,0x2ef538d1,0xba93b6a4,0xbb24bbfb,0xbbfeb9a6,0x305bb91f,0x3bcb3a97,0xb50b37d2,
  0xb87abbfe,0x3ba13546,0x24523a7e,0xbbb5ba54,0x3a733aa5,0xbbfcb487,0x39d6b654,0xafef3b21,0x1cb63bc3,0xb7b2bbbf,0x3aba39da,0xbbfab517,
  0x398b39cd,0x38fd3946,0x386538b2,0x37853815,0xba85b9c9,0xbb92bb1e,0xbbfebbdd,0xbbc2bbf5,0x319e389e,0xb929b426,0xbc00bb45,0xb911bb37,
  0xbbffbac1,0xb805bafe,0x382a217f,0x3bfd3b13,0xb66b3682,0xbb01bb94,0x387fb371,0x3a2d3beb,0xbac7bb76,0x3a00ad33,0x36bb3bd4,0xbbeab79b,
  0xbabd330f,0x34dbba58,0x36023bfe,0xbb0db9f4,0xb68dbbe1,0x3a5c3a45,0xbbe7b648,0x3b89adfb,0xb9c5b982,0xba41ba04,0xbab0ba7a,0xbb10bae1,
  0xb8a3b986,0xb52fb74e,0xa94db1e8,0x33d32e91,0xbbe0ba89,0xba1dbbba,0x1fdbb6af,0x3a3136e8,0xa776b84a,0x3aeb37c8,0x3ad53c00,0xaa7a377a,
  0xbb54bb4f,0x37bdb523,0x3a9e3bc8,0xb916308d,0x3840b5c8,0x394a3bf9,0xbb42b294,0xb0a6bb0a,0xb850bbce,0x3b9f38e0,0xbb6a28e8,0x3790b958,
  0x3b4cb185,0xb8db38f8,0x30f0bb5c,0x355e3bf7,0x363136dd,0x34cf3581,0x32c6341a,0x2fbd3153,0xbae1bb65,0xb970ba39,0xb715b889,0xb16cb4f3,
  0x3219b3d3,0x3b0438b7,0x3b713bfc,0x34ff397d,0x36e83aa9,0xb8b2adc9,0xbbefbb59,0xb5bcba49,0xb9a12a7a,0xb924bbfe,0x3a933042,0x37dd3bcc,
  0x308db9aa,0x3b453b07,0xb94632ad,0xb845bbfa,0x3bd730a6,0xb902382a,0xa452bb92,0x39373b7a,0xb9583874,0x3371bb16,0x34263c00,0xb982bafb,
  0xbb60bb3a,0xbba1bb83,0xbbd2bbbc,0xbbf1bbe3,0x3815361a,0x39df3907,0x3b2c3a97,0x3be23b9c,0x3bda3bc2,0x37b23a76,0xb5df2c06,0xbb9ab9d2,
  0xbb37b86f,0xba7abbf8,0x3029b654,0x3b7838f3,0xb9afbbfd,0x3a21294d,0x388e3bee,0xbaf7b328,0x3beb39a6,0xb6af37a6,0xba04bbd3,0x3ac42d00,
  0x32633bea,0xba3dbad5,0x3c00352f,0xba1135b1,0xb9f4baa5,0x3bc8376f,0xbbba2311,0x39cdb7d2,0x3b7a3bf1,0x394a3a93,0x33893764,0xb3d39cb6,
  0x3afb3be2,0x35eb3946,0xb4c328e8,0xbaa9b8cc,0x38a33b9a,0xb8dba452,0xbb83bbae,0x2a7ab86a,0x37423b78,0xbab6b426,0xb907bbe6,0x39aa2ade,
  0x27763af7,0xbb2fbaba,0x3a76ad97,0x30a63b60,0xaf8b3ac4,0xb994bb94,0x3bf8358d,0xb8743815,0xb8403a11,0x341abb57,0x294d3bf4,0xb55ebbda,
  0xb93339cd,0x3889ba58,0xb7a63ad1,0x3625bb37,0xb5b1afbd,0xba00b88e,0xbbc6bb18,0xbbc2bc00,0xb7d2b16c,0xbb6fba04,0xbba3bbfe,0xb86fba67,
  0xba85b4ff,0xba5cbc00,0x3581b47b,0x3bfd3aac,0xbb21b5bc,0xb85abbba,0x3a393109,0x39a63bfd,0xbbffb7dd,0x370ab855,0x38b73bf8,0xbbeab631,
  0xbbf2b845,0x39bcb523,0x2dc93b81,0xbaa5bae1,0xbac7b937,0x3bbc365f,0xbbfeaef5,0x3b89b219,0xba15b982,0x3a9738e0,0xbb07b830,0x3b6336e8,
  0xb958b785,0xbb81ba9e,0xbbefbbf3,0xba89bb73,0xbbf7bbc2,0xb9b8bb42,0xaf59b70a,0x384a3328,0x3bc03911,0x38303b6a,0xb946ad65,0xbb4fbbd0,
  0x3a353bfd,0xb85f30f0,0xbb1ebbbc,0x35c8b5b1,0xbb8bba2d,0x39dfb27c,0x34263bb0,0xbbceb98b,0xb4b7bbea,0x3b6c39e3,0xbafe2c06,0x3185ba85,
  0x38cc3b0d,0xba7ab99d,0x3b943759,0xbbffb19e,0xb4933b89,0x31e8bbc6,0xad333bee,0xa5e4bbff,0xb9f4bb10,0xb58db87f,0x3029af27,0x389e35d4,
  0x2dfbb3d3,0x399936bb,0x3bf23b2f,0x3ac13bcc,0x33eb3a31,0xbad1b602,0xba04bbf9,0x3682b2de,0xb90c2a7a,0xbab3bbe7,0x374eb41a,0x3b763b7a,
  0x3552b916,0x39703bd6,0xbbbab46f,0x330fb9c5,0x3ba530a6,0xb5f7396b,0xb7c8bbfc,0x3be138a3,0xba673790,0x38b2b9b3,0xb5233b1b,0x26adbbe0,
  0xbbabb55e,0x3bdd3389,0xbbf9b042,0x3bff2776,0xb742b93c,0x2311b340,0x37a6340e,0x3aa93966,0x3b963a4d,0x3b7f3c00,0x380f3a21,0xb0be3219,
  0x2f8bb7e8,0x3bde3979,0x376f3b32,0xb9aab0d7,0x3bb83b24,0xb1223855,0xbbfdba3d,0xaa16b9a1,0x3933b50b,0x35eb3be4,0xbbf5b8d6,0x3874b6c6,
  0x39413bb5,0xbbffb65f,0x38d1b764,0x33ba3bd7,0x3bb3afef,0xbab63699,0x391fb94f,0xb6253ad8,0x30103bfa,0xb359bbdf,0x35463bae,0xb6d2bb68,
  0x3b213a0d,0x3c003bcb,0x3b073bbd,0x386f39e7,0x351738ee,0xb599a452,0xbae5b924,0xbbe9bbda,0x3bf23af4,0x31cf39d6,0xbb16b6ff,0xb9a6bbe8,
  0xb4323737,0xbbe5baba,0x2b43b902,0x3bfe39af,0x3a153b98,0xbb6fb13b,0x2ec3ba60,0x3aa53b3f,0xba09344b,0xa884bb57,0x3a643b18,0xbbc3b263,
  0x34573bf0,0xb85abb4a,0x3a2539fc,0xbb63b825,0xbbef2cce,0x3bc9b1b6,0xbb8e347b,0x3b3db60e,0x3bf53b87,0x3b6c3bec,0x392e3a7e,0x32f73721,
  0xb9e7b785,0xbbfcbb5e,0xba81bbb0,0xb43eb894,0xbb13bbe9,0x31e8b6f4,0x3bf239da,0x36763af1,0x3be83911,0x340e3ab0,0xbb7cb759,0xb72cbb73,
  0x379b3bfe,0xbc00b80f,0x374eb835,0x38993bfb,0xbb3fba2d,0x3b329fdb,0xb3403a41,0xb8eabbd0,0x2dfbbbc3,0x32943bfd,0xb7c8bb7f,0x39c93a54,
  0x38253b0d,0xb8d6ba9e,0x39793a1d,0xba0db98b,0x2e91356a,0xb5f7b074,0xba19b8ad,0xbbcfbb2a,0xb966bb10,0xaba7b63c,0x38a8346f,0x3bb73a90,
  0x377ab0be,0x3bdd3b35,0x2f593974,0xbb52b7f3,0x30d73a31,0xbbbdb865,0xb5a5bb1b,0x3b2735d4,0xbb0aaa16,0xa17fbae5,0x3b1e3ace,0xba8c2c6a,
  0x36c6b916,0x36ff3c00,0xbbcbb8fd,0x3a50b2de,0x3bf733ba,0xbbd42b43,0x3afeb599,0xb98638e5,0xbad83790,0x3a60b87f,0xb9d63929,0x393cb9c5,
  0xba093986,0x3a7eb8f8,0xbae5385f,0x3b3db77a,0xbabd393c,0x3bb0b699,0xbc00305b,0x3ba730d7,0xbbef384a,0x39da34e7,0x2b43bb6c,0xba6f3b0a,
  0xbc0037e8,0x3759383a,0x387fbbfc,0xbbf636c6,0xbb2a35c8,0xb8353bb2,0x3a64b1e8,0x3962bbf7,0xba90350b,0xba413bff,0x3602340e,0x3bf6bad8,
  0xb7f33185,0xbb7f3a19,0xbb8e3c00,0xb8203a35,0xb5d42fef,0xba1d38a8,0xbbd63b32,0xbba93bfe,0xb941b9c9,0x38ad3a45,0xb80fbab3,0x36d23b13,
  0xb850ba0d,0x346f3b4a,0x1fdbbbed,0xb4ab3be8,0xb010bac1,0xb9743b9e,0x3bfdb5f7,0xb8c1b79b,0x251bbaf4,0xbb1b3acb,0x3a9e2ba7,0x2e5fbb3f,
  0x3721bb76,0xbace3463,0xb8d13bdd,0x39ebadfb,0x3894bb98,0xb8fd281f,0xbb6a3bbd,0x2e2d3825,0x3af1bbe1,0x3599b92e,0xb546a17f,0xbadb390c,
  0x3b73bbf0,0x3929ba81,0x327cb6ff,0xb49f29b1,0xbb853625,0x3bbdb4c3,0xbbe432ad,0x3bfbaf8b,0xbaacb6d2,0x39243954,0xb65fbace,0x2fbd3bb8,
  0x3bc5b24b,0xb6ffb907,0xb6993c00,0x3bb7b933,0x363138c1,0x3902bbec,0xbbdf3599,0x34ff3941,0xb9661648,0xba603bf8,0x383a31cf,0x3b27bbb3,
  0x3219b9eb,0xbb1836f4,0xb9903be5,0x37dd3010,0x30d73232,0x39fcb7a6,0x3bffbb6f,0x3a50bb9c,0xb9a13adb,0xb47b380f,0x32c62884,0x3937b721,
  0xb576bb63,0x340e3ba3,0xb13bbbd3,0x2c9c3bf2,0x386abb3d,0xba2139f8,0x3b57b835,0xbbf13432,0xb3a23bd8,0x3b32ba39,0xbb4a2311,0x343e3a15,
  0xbb603a6f,0x3a3d3074,0x31b6bb7f,0xbb9a3a09,0x39e7bc00,0xb8d6adc9,0xbacb3bde,0x372c3457,0x3bdab962,0x3764bb35,0xb9c03122,0xbaf73bef,
  0xbbe83bd9,0xb94f3b07,0xa81f35eb,0x38eab4f3,0xb9af3820,0xbbae3ae5,0xbbd23bff,0xba113b2a,0xbc0026ad,0x3bf32c38,0xbbd6b109,0x3ba733eb,
  0x3153bbff,0xb70a3b9e,0x396bba9b,0xbade390c,0xba90b16c,0x2d653aee,0x39b3bb81,0xbbf63552,0x397dbbcf,0xbbbc3463,0x338939b8,0x39f0bba5,
  0xb5d4b5bc,0xbbb03b2c,0x32013830,0x3bf6ba67,0x3bccbb52,0x2c06b92e,0xbb83385f,0xb8c73bab,0x32deb845,0xb7593029,0xbb5e39df,0xbba93bfd,
  0x3b7aba8c,0x3beebbf2,0x3a76bb6c,0x36ddb91b,0x251bbbff,0xaf273bfc,0x327cbbe6,0xb4ab3bc0,0x3be325e4,0xbb2fb4e7,0x39e33884,0xb81aba35,
  0x3894bbe2,0xbbf937fe,0x399d358d,0x2e5fbb8b,0x39d232f7,0x341abbb2,0xbbc63999,0x395d34b7,0x3b73bb78,0xb46fb715,0xbbdc3ad1,0x2e2d38cc,
  0x33283676,0x3bfcba19,0x3581bab3,0xba6b3493,0x3bd0bac4,0x3b1bbbef,0x363cb970,0xb49faade,0xb5b13899,0x30422f59,0x38b7b5f7,0x3b3aba29,
  0xbb68b55e,0x3b1836bb,0xbabab805,0x3a4d38a3,0x3bc0b625,0xbbfe2ec3,0x3b9431cf,0xba89b742,0x387a381a,0x347bbbe7,0xbb573a00,0x3b242776,
  0xbb8b324b,0x31093a25,0x3a58bb6f,0xbb4f2f8b,0x9cb6b95d,0xbbf8396b,0xb1b63a5c,0x3bb5b840,0x38cc9648,0x3b81bbac,0xac38b85a,0xbbce3933,
  0xb86a3a6b,0x2ef53389,0x39c0b70a,0x3bfabb4c,0xaadeb232,0xb83034c3,0xbaee39bc,0xbbff3bb3,0x360ebb89,0xb7643b42,0x3855baeb,0xb8ee3a85,
  0x33eb3b63,0x28e8bbf5,0xb5233bde,0x389ebb21,0xbaa23ade,0x3baeb0f0,0xb65fb94a,0xb7373bff,0x3552bbd8,0xbbe6391f,0x38e035eb,0x3682bbf2,
  0x3c00b9f0,0x2d97b9e3,0xbbdf38db,0xb44b3ac7,0xba673c00,0x358d3487,0x3bfcbab6,0x330fba15,0xbaac38c7,0xbbf43bc6,0xb9903b2f,0xacce368d,
  0x3bfdbbd9,0x3ad1bba3,0x37feb994,0x26adb457,0xbb4c38ee,0x3bfcb1b6,0xbad5b4cf,0x381a39af,0xbbb3389e,0x3b592c38,0xb76fb970,0xb24b3beb,
  0xbbe33737,0x304239c0,0x3b42bb04,0xb95db263,0xbb9c3682,0xb2ad3aee,0x3bf5b8b2,0x1648b9f4,0xb9d2344b,0xbb923bd2,0xb0f03924,0x3a6bb60e,
  0xb8f3330f,0xbc003b2c,0xb91f3b45,0x323233eb,0xb3282cce,0xb80535df,0xb9e33902,0xbb3a3aa2,0xad0026ad,0xb1cf3029,0xb4873371,0xb61a3552,
  0xb68dba4d,0xac063bdf,0x382abba1,0xbade39a1,0xb457ba89,0xb6543bfc,0x3b16b9df,0xbbd8308d,0x3153bb24,0xbbee3990,0x36bb37b2,0x39f0bbd7,
  0x34f3bb4f,0xbbd337fe,0xaec33a7a,0x3c00b958,0x397dbbb5,0xb52fb2c6,0xbbe73a21,0xb8c73b68,0x3a49bbce,0x2311b715,0xba2536af,0xbbd93bc0,
  0x3bccbbfa,0x3aebbb71,0x396bba3d,0x36ddb87a,0x3bfabbff,0x3bdebbef,0x3bacbbc8,0x3b65bb8b,0xaadebba7,0xb6af3bdc,0x3a58ba41,0xbbe2366b,
  0x3a29bade,0xbc003581,0x3a45352f,0xb2f7bac7,0xb8153bf6,0x3bc8b63c,0xac38ba1d,0xbb783abd,0xbbf539f0,0x329438b7,0x3b9ebaeb,0xb676b68d,
  0x3b37bbf6,0x28e8b865,0xbaee37bd,0xbac43c00,0x3b13b8c7,0x3b5cbbfe,0x3463b94a,0xb8993153,0xbbeb3ba9,0xbbe63c00,0xbb2c3b9f,0xb9cd3a90,
  0xb79b36dd,0xb884382a,0xb92e38db,0xb9c9397d,0x3bfdb4ab,0xbb45b201,0x38e038fd,0xb16cbb54,0x391b381a,0xa17fbb83,0xb8f83b92,0x3bcfb840,
  0xbae12e5f,0xb3713b5e,0x3bfcb929,0xb5bcb850,0xae91b95d,0xbbd43a76,0x34e73805,0x3b52bb4c,0x36e82e2d,0x3bfebab0,0x37febb01,0xb845251b,
  0xb77a3a6b,0x3648294d,0x3bb2ba00,0x3a8cbbe3,0x308db49f,0xb1091fdb,0xb71534db,0xb9823894,0x3b0abb3a,0x3a9bbad5,0x3a19ba5c,0x3986b9d2,
  0x3b9c2c9c,0xb994b83a,0x34873ae8,0x324bbbfe,0xb7213bf1,0x3b47b990,0xbbbf2d97,0x38c1387a,0x38f3343e,0x3889bbff,0xbba3353a,0x96483a73,
  0xbaf13b9a,0x38ad32c6,0x39f8bbf4,0xb9eb9cb6,0x2d00372c,0x3b59b8a8,0x3a39bbed,0xb232b576,0xbbfb3af7,0xb9743b71,0x307434cf,0x3adbb86a,
  0xb7d238ea,0xb2ad35a5,0x2dc92ba7,0x361ab3a2,0xba543a11,0xbace3a93,0xbb353b04,0xbb873b60,0xb4f33bfb,0x39bcbacb,0xbbac380a,0x3bd8a9b1,
  0xbb2aafbd,0x36a439c0,0x3402bbf8,0xba6f3aa2,0xba493bb7,0x3a97a81f,0x34c3bb90,0xbc0038bc,0xb7f3b4ff,0xba7e3bd2,0x39542ef5,0x3962bc00,
  0xbbfa3b27,0xb6543a81,0x3907b05b,0x3bd9bb85,0x2c6ab7dd,0xb9da35df,0xbbec3ba1,0xb8203aac,0xbafb3a50,0xbbd33b7c,0xbbf83bfc,0xbb653bc5,
  0x38e5b937,0x3835b88e,0x36f4b7b2,0x356ab631,0xb90c3b3d,0x3b5cb8d1,0xbbf93122,0x3ac13517,0x29b1bba7,0xb94f3b6a,0x3be4b7bd,0xbaf4b19e,
  0x3ba5ba6f,0xb884b546,0xb8f83bff,0x3b76b432,0xb8bc3bf6,0x3ae8b27c,0x3699bb9f,0xbb98366b,0xbbab3962,0xb9993bbf,0x34e73359,0x3be1ba09,
  0x3b85bbf6,0x353ab99d,0xb83a2f27,0xbbf03abd,0x391bb820,0x3ab3b9f8,0x3bb2bb47,0x3bffbbef,0xbbc53ba9,0xbbed3bdc,0xbbff3bf9,0xbbfb3c00,
  0xba35b6d2,0x36483a64,0x2d33bbe5,0xb84a3b96,0x3bfeb4ab,0xb9fcb602,0x313b3b01,0x37e8bbe0,0x34b738c1,0x3a9bbb8e,0xba45a884,0xb5c83bb8,
  0xba732e5f,0xb80a3bd6,0x3b4ab4db,0x350bbb54,0x3493b9eb,0xb9b83402,0xbb9e3bc9,0xb1853941,0x35762e2d,0x3b90b9b3,0x3acbbbf3,0x2fefb850,
  0xba293adb,0xb85f3954,0xb46336a4,0x25e43010,0x33a2b49f,0x305bb201,0x281fad65,0xac9c251b,0x3f803f80,0x3f803f80,0x3f803f80,0x3f803f80,
  0x3f803f80,0x3f803f80,0x3f803f80,0x3f803f80,0x3f803f80,0x3f803f80,0x3f803f80,0x3f803f80,0x3f803f80,0x3f803f80,0x3f803f80,0x3f803f80,
  0x3f803f80,0x3f803f80,0x3f803f80,0x3f803f80,0x3f803f80,0x3f803f80,0x3f803f80,0x3f803f80,0x3f803f80,0x3f803f80,0x3f803f80,0x3f803f80,
  0x3f803f80,0x3f803f80,0x3f803f80,0x3f803f80,0x3f803f80,0x3f803f80,0x3f803f80,0x3f803f80,0x3f803f80,0x3f803f80,0x3f803f80,0x3f803f80,
  0x3f803f80,0x3f803f80,0x3f803f80,0x3f803f80,0x3f803f80,0x3f803f80,0x3f803f80,0x3f803f80,0x3f803f80,0x3f803f80,0x3f803f80,0x3f803f80,
  0x3f803f80,0x3f803f80,0x3f803f80,0x3f803f80,0x3f803f80,0x3f803f80,0x3f803f80,0x3f803f80,0x3f803f80,0x3f803f80,0x3f803f80,0x3f803f80,
  0x3f803f80,0x3f803f80,0x3f803f80,0x3f803f80,0x3f803f80,0x3f803f80,0x3f803f80,0x3f803f80,0x3f803f80,0x3f803f80,0x3f803f80,0x3f803f80,
  0x3f803f80,0x3f803f80,0x3f803f80,0x3f803f80,0x3f803f80,0x3f803f80,0x3f803f80,0x3f803f80,0x3f803f80,0x3f803f80,0x3f803f80,0x3f803f80,
  0x3f803f80,0x3f803f80,0x3f803f80,0x3f803f80,0x3f803f80,0x3f803f80,0x3f803f80,0x3f803f80,0x3f803f80,0x3f803f80,0x3f803f80,0x3f803f80,
  0x3f803f80,0x3f803f80,0x3f803f80,0x3f803f80,0x3f803f80,0x3f803f80,0x3f803f80,0x3f803f80,0x3f803f80,0x3f803f80,0x3f803f80,0x3f803f80,
  0x3f803f80,0x3f803f80,0x3f803f80,0x3f803f80,0x3f803f80,0x3f803f80,0x3f803f80,0x3f803f80,0x3f803f80,0x3f803f80,0x3f803f80,0x3f803f80,
  0x3f803f80,0x3f803f80,0x3f803f80,0x3f803f80,0x3f803f80,0x3f803f80,0x3f803f80,0x3f803f80,0x3f803f80,0x3f803f80,0x3f803f80,0x3f803f80,
  0x3f803f80,0x3f803f80,0x3f803f80,0x3f803f80,0x3f803f80,0x3f803f80,0x3f803f80,0x3f803f80,0x3f803f80,0x3f803f80,0x3f803f80,0x3f803f80,
  0x3f803f80,0x3f803f80,0x3f803f80,0x3f803f80,0x3f803f80,0x3f803f80,0x3f803f80,0x3f803f80,0x3f803f80,0x3f803f80,0x3f803f80,0x3f803f80,
  0x3f803f80,0x3f803f80,0x3f803f80,0x3f803f80,0x3f803f80,0x3f803f80,0x3f803f80,0x3f803f80,0x3f803f80,0x3f803f80,0x3f803f80,0x3f803f80,
  0x3f803f80,0x3f803f80,0x3f803f80,0x3f803f80,0x3f803f80,0x3f803f80,0x3f803f80,0x3f803f80,0x3f803f80,0x3f803f80,0x3f803f80,0x3f803f80,
  0x3f803f80,0x3f803f80,0x3f803f80,0x3f803f80,0x3f803f80,0x3f803f80,0x3f803f80,0x3f803f80,0x3f803f80,0x3f803f80,0x3f803f80,0x3f803f80,
  0x3f803f80,0x3f803f80,0x3f803f80,0x3f803f80,0x3f803f80,0x3f803f80,0x3f803f80,0x3f803f80,0x3f803f80,0x3f803f80,0x3f803f80,0x3f803f80,
  0x3f803f80,0x3f803f80,0x3f803f80,0x3f803f80,0x3f803f80,0x3f803f80,0x3f803f80,0x3f803f80,0x3f803f80,0x3f803f80,0x3f803f80,0x3f803f80,
  0x3f803f80,0x3f803f80,0x3f803f80,0x3f803f80,0x3f803f80,0x3f803f80,0x3f803f80,0x3f803f80,0x3f803f80,0x3f803f80,0x3f803f80,0x3f803f80,
  0x3f803f80,0x3f803f80,0x3f803f80,0x3f803f80,0x3f803f80,0x3f803f80,0x3f803f80,0x3f803f80,0x3f803f80,0x3f803f80,0x3f803f80,0x3f803f80,
  0x3f803f80,0x3f803f80,0x3f803f80,0x3f803f80,0x3f803f80,0x3f803f80,0x3f803f80,0x3f803f80,0x3f803f80,0x3f803f80,0x3f803f80,0x3f803f80,
  0x3f803f80,0x3f803f80,0x3f803f80,0x3f803f80,0x3f803f80,0x3f803f80,0x3f803f80,0x3f803f80,0x3f803f80,0x3f803f80,0x3f803f80,0x3f803f80,
  0x3f803f80,0x3f803f80,0x3f803f80,0x3f803f80,0x3f803f80,0x3f803f80,0x3f803f80,0x3f803f80,0x3f803f80,0x3f803f80,0x3f803f80,0x3f803f80,
  0x3f803f80,0x3f803f80,0x3f803f80,0x3f803f80,0x3f803f80,0x3f803f80,0x3f803f80,0x3f803f80,0x3f803f80,0x3f803f80,0x3f803f80,0x3f803f80,
  0x3f803f80,0x3f803f80,0x3f803f80,0x3f803f80,0x3f803f80,0x3f803f80,0x3f803f80,0x3f803f80,0x3f803f80,0x3f803f80,0x3f803f80,0x3f803f80,
  0x3f803f80,0x3f803f80,0x3f803f80,0x3f803f80,0x3f803f80,0x3f803f80,0x3f803f80,0x3f803f80,0x3f803f80,0x3f803f80,0x3f803f80,0x3f803f80,
  0x3f803f80,0x3f803f80,0x3f803f80,0x3f803f80,0x3f803f80,0x3f803f80,0x3f803f80,0x3f803f80,0x3f803f80,0x3f803f80,0x3f803f80,0x3f803f80,
  0x3f803f80,0x3f803f80,0x3f803f80,0x3f803f80,0x3f803f80,0x3f803f80,0x3f803f80,0x3f803f80,0x3f803f80,0x3f803f80,0x3f803f80,0x3f803f80,
  0x3f803f80,0x3f803f80,0x3f803f80,0x3f803f80,0x3f803f80,0x3f803f80,0x3f803f80,0x3f803f80,0x3f803f80,0x3f803f80,0x3f803f80,0x3f803f80,
  0x3f803f80,0x3f803f80,0x3f803f80,0x3f803f80,0x3f803f80,0x3f803f80,0x3f803f80,0x3f803f80,0x3f803f80,0x3f803f80,0x3f803f80,0x3f803f80,
  0x3f803f80,0x3f803f80,0x3f803f80,0x3f803f80,0x3f803f80,0x3f803f80,0x3f803f80,0x3f803f80,0x3f803f80,0x3f803f80,0x3f803f80,0x3f803f80,
  0x3f803f80,0x3f803f80,0x3f803f80,0x3f803f80,0x3f803f80,0x3f803f80,0x3f803f80,0x3f803f80,0x3f803f80,0x3f803f80,0x3f803f80,0x3f803f80,
  0x3f803f80,0x3f803f80,0x3f803f80,0x3f803f80,0x3f803f80,0x3f803f80,0x3f803f80,0x3f803f80,0x3f803f80,0x3f803f80,0x3f803f80,0x3f803f80,
  0x3f803f80,0x3f803f80,0x3f803f80,0x3f803f80,0x3f803f80,0x3f803f80,0x3f803f80,0x3f803f80,0x3f803f80,0x3f803f80,0x3f803f80,0x3f803f80,
  0x3f803f80,0x3f803f80,0x3f803f80,0x3f803f80,0x3f803f80,0x3f803f80,0x3f803f80,0x3f803f80,0x3f803f80,0x3f803f80,0x3f803f80,0x3f803f80,
  0x3f803f80,0x3f803f80,0x3f803f80,0x3f803f80,0x3f803f80,0x3f803f80,0x3f803f80,0x3f803f80,0x3f803f80,0x3f803f80,0x3f803f80,0x3f803f80,
  0x3f803f80,0x3f803f80,0x3f803f80,0x3f803f80,0x3f803f80,0x3f803f80,0x3f803f80,0x3f803f80,0x3f803f80,0x3f803f80,0x3f803f80,0x3f803f80,
  0x3f803f80,0x3f803f80,0x3f803f80,0x3f803f80,0x3f803f80,0x3f803f80,0x3f803f80,0x3f803f80,0x3f803f80,0x3f803f80,0x3f803f80,0x3f803f80,
  0x3f803f80,0x3f803f80,0x3f803f80,0x3f803f80,0x3f803f80,0x3f803f80,0x3f803f80,0x3f803f80,0x3f803f80,0x3f803f80,0x3f803f80,0x3f803f80,
  0x3f803f80,0x3f803f80,0x3f803f80,0x3f803f80,0x3f803f80,0x3f803f80,0x3f803f80,0x3f803f80,0x3f803f80,0x3f803f80,0x3f803f80,0x3f803f80,
  0x3f803f80,0x3f803f80,0x3f803f80,0x3f803f80,0x3f803f80,0x3f803f80,0x3f803f80,0x3f803f80,0x3f803f80,0x3f803f80,0x3f803f80,0x3f803f80,
  0x3f803f80,0x3f803f80,0x3f803f80,0x3f803f80,0x3f803f80,0x3f803f80,0x3f803f80,0x3f803f80,0x3f803f80,0x3f803f80,0x3f803f80,0x3f803f80,
  0x3f803f80,0x3f803f80,0x3f803f80,0x3f803f80,
};

__device__ __align__(128) float    g_part[16][8][2176];
__device__ __align__(128) float    g_kv[16][2176];
constexpr int OBLK = 16 * 1024 + 32;
__device__ __align__(128) uint4    g_o[16 * OBLK];
#define GSTAMP(role, i) do {} while (0)
#define STAMP(role, i) do {} while (0)
#define PDUMP(role) do {} while (0)
#define PROF_SMEM 0

constexpr int STAGE_BYTES = 57344;
constexpr int OFF_H = 4 * 16384, OFF_VP = 9 * 16384, OFF_SPARE = 10 * 16384;
constexpr int OFF_XT = 172032, XT_STRIDE = 4112;
constexpr int OFF_BAR = 204928, OFF_EPOCH = OFF_BAR + 640, OFF_EX = OFF_BAR + 656, OFF_D = OFF_BAR + 672, OFF_SCALE = OFF_BAR + 704;
constexpr int OFF_F2F = 205824, OFF_F2I = 207872, OFF_F4 = 209920, OFF_ONES = 214016, OFF_KVB = 214016;
constexpr int OFF_STG = 219136, STG_STRIDE = 4352, SMEM_TOTAL = 232192 + PROF_SMEM;
enum { B_FULL1 = 0, B_EMPTY1 = 3, B_Q = 6, B_ODONE1 = 7, B_O1RDY = 8, B_H = 9, B_XRAW = 10, B_XT = 11, B_KV = 12, B_Y = 13,  B_AFREE = 15,
       B_STG = 18, B_ODONE = 24, B_XFREE = 25, B_FULL2 = 33, B_CONS2 = 49, B_SFREE = 14, B_KV1 = 61, B_OLOC = 60, B_PKRDY = 62, B_PKFREE = 64, B_H2 = 65, B_G1DONE = 66, B_COUNT = 67, B_FIRST = 67 };
constexpr uint64_t SLOT_A = 0x6859468594685948ull, SLOT_B = 0x7103271032710326ull;
constexpr int NPRE = 6, BEARLY = 3;
__host__ __device__ constexpr int bar_count(int i) {
  return i < B_EMPTY1 ? 1 : i < B_Q ? 4 : i == B_XT ? 4 : i == B_H ? 4 : (i == B_SFREE || i == B_G1DONE) ? 2 : i >= B_PKFREE ? 4 : i >= B_PKRDY ? 8 : i == B_Y ? 9
       : (i >= B_AFREE && i < B_STG) ? 16 : (i == B_ODONE || i == B_ODONE1) ? 8 : (i >= B_XFREE && i < B_FULL2) ? 4
       : i == B_KV1 ? 1 : i == B_OLOC ? 2 : i >= B_CONS2 ? 4 : (i >= B_FULL2 && i < B_FULL2 + NPRE) ? 2 : 1;
}
__host__ __device__ constexpr uint64_t bar_counts(int r) {
  uint64_t v = 0;
  for (int w = 0; w < 11; w++) v |= (uint64_t)(bar_count(1 + 11 * r + w) - 1) << (4 * w);
  return v;
}
constexpr uint32_t SW128 = 64 | (1u << 30);
constexpr int SPIN_LIMIT = 1 << 22;
#define RC 200
#define PFD 3
#define QPF 6
#define D1 100
#define HSTART 1500
#define PACE 800
#define BPACE 250
#define PD1 700
#define PD2 450
#define OCH 3
#define O1D 0
#define TRICK 3
#define HOLD2 12

__device__ __forceinline__ uint32_t smem_u32(const void* p) { return (uint32_t)__cvta_generic_to_shared(p); }
__device__ __forceinline__ void wg_fence() { asm volatile("wgmma.fence.sync.aligned;" ::: "memory"); }
__device__ __forceinline__ void wg_commit() { asm volatile("wgmma.commit_group.sync.aligned;" ::: "memory"); }
template <int N> __device__ __forceinline__ void wg_wait() { asm volatile("wgmma.wait_group.sync.aligned %0;" ::"n"(N) : "memory"); }
template <int N> __device__ __forceinline__ void keep(float (&d)[N]) {
#pragma unroll
  for (int i = 0; i < N; i++) asm volatile("" : "+f"(d[i])::"memory");
}
__device__ __forceinline__ void mbar_init(uint32_t bar, int cnt) { asm volatile("mbarrier.init.shared::cta.b64 [%0], %1;" ::"r"(bar), "r"(cnt)); }
__device__ __forceinline__ void mbar_expect(uint32_t bar, int bytes) { asm volatile("mbarrier.arrive.expect_tx.shared::cta.b64 _, [%0], %1;" ::"r"(bar), "r"(bytes) : "memory"); }
__device__ __forceinline__ void mbar_arrive(uint32_t bar) { asm volatile("mbarrier.arrive.shared::cta.b64 _, [%0];" ::"r"(bar) : "memory"); }
__device__ __forceinline__ void mbar_arrive_cl(uint32_t bar, uint32_t cta) {
  asm volatile("{\n.reg .b32 r;\nmapa.shared::cluster.u32 r, %0, %1;\nmbarrier.arrive.shared::cluster.b64 _, [r];\n}\n" ::"r"(bar), "r"(cta) : "memory");
}
__device__ __forceinline__ void mbar_wait(uint32_t bar, uint32_t parity) {
  asm volatile("{\n.reg .pred p;\n.reg .u32 n;\nmov.u32 n, 0;\n"
               "W_%=:\nmbarrier.try_wait.parity.shared::cta.b64 p, [%0], %1;\n@p bra D_%=;\n"
               "add.u32 n, n, 1;\nsetp.lt.u32 p, n, %2;\n@p bra W_%=;\ntrap;\nD_%=:\n}\n" ::"r"(bar), "r"(parity), "n"(SPIN_LIMIT) : "memory");
}
__device__ __forceinline__ void fence_async() { asm volatile("fence.proxy.async.shared::cta;" ::: "memory"); }
__device__ __forceinline__ void bar_sync(int id) { asm volatile("bar.sync %0, 128;" ::"r"(id) : "memory"); }
__device__ __forceinline__ void tma2d(uint32_t dst, const CUtensorMap* m, int c0, int c1, uint32_t bar) {
  asm volatile("cp.async.bulk.tensor.2d.shared::cluster.global.mbarrier::complete_tx::bytes [%0], [%1, {%3, %4}], [%2];"
               ::"r"(dst), "l"(m), "r"(bar), "r"(c0), "r"(c1) : "memory");
}
__device__ __forceinline__ void tma2d_mc(uint32_t dst, const CUtensorMap* m, int c0, int c1, uint32_t bar) {
  asm volatile("cp.async.bulk.tensor.2d.shared::cluster.global.mbarrier::complete_tx::bytes.multicast::cluster [%0], [%1, {%3, %4}], [%2], %5;"
               ::"r"(dst), "l"(m), "r"(bar), "r"(c0), "r"(c1), "h"((uint16_t)3) : "memory");
}
__device__ __forceinline__ void tma3d(uint32_t dst, const CUtensorMap* m, int c0, int c1, int c2, uint32_t bar) {
  asm volatile("cp.async.bulk.tensor.3d.shared::cluster.global.mbarrier::complete_tx::bytes [%0], [%1, {%3, %4, %5}], [%2];"
               ::"r"(dst), "l"(m), "r"(bar), "r"(c0), "r"(c1), "r"(c2) : "memory");
}
__device__ __forceinline__ void tma4d(uint32_t dst, const CUtensorMap* m, int c0, int c1, int c2, int c3, uint32_t bar) {
  asm volatile("cp.async.bulk.tensor.4d.shared::cluster.global.mbarrier::complete_tx::bytes [%0], [%1, {%3, %4, %5, %6}], [%2];"
               ::"r"(dst), "l"(m), "r"(bar), "r"(c0), "r"(c1), "r"(c2), "r"(c3) : "memory");
}
__device__ __forceinline__ void bulk_ld(uint32_t dst, const void* src, int bytes, uint32_t bar) {
  asm volatile("cp.async.bulk.shared::cluster.global.mbarrier::complete_tx::bytes [%0], [%1], %2, [%3];" ::"r"(dst), "l"(src), "r"(bytes), "r"(bar) : "memory");
}
__device__ __forceinline__ void bulk_ld_mc(uint32_t dst, const void* src, int bytes, uint32_t bar) {
  asm volatile("cp.async.bulk.shared::cluster.global.mbarrier::complete_tx::bytes.multicast::cluster [%0], [%1], %2, [%3], %4;"
               ::"r"(dst), "l"(src), "r"(bytes), "r"(bar), "h"((uint16_t)3) : "memory");
}
__device__ __forceinline__ void tma2d_st(const CUtensorMap* m, uint32_t src, int c0, int c1) {
  asm volatile("cp.async.bulk.tensor.2d.global.shared::cta.bulk_group [%0, {%2, %3}], [%1];" ::"l"(m), "r"(src), "r"(c0), "r"(c1) : "memory");
}
__device__ __forceinline__ void ldsm4(uint32_t (&r)[4], uint32_t a) {
  asm volatile("ldmatrix.sync.aligned.m8n8.x4.shared.b16 {%0,%1,%2,%3}, [%4];" : "=r"(r[0]), "=r"(r[1]), "=r"(r[2]), "=r"(r[3]) : "r"(a) : "memory");
}
__device__ __forceinline__ void ldsm4t(uint32_t (&r)[4], uint32_t a) {
  asm volatile("ldmatrix.sync.aligned.m8n8.x4.trans.shared.b16 {%0,%1,%2,%3}, [%4];" : "=r"(r[0]), "=r"(r[1]), "=r"(r[2]), "=r"(r[3]) : "r"(a) : "memory");
}
__device__ __forceinline__ void stsm4(uint32_t a, uint32_t r0, uint32_t r1, uint32_t r2, uint32_t r3) {
  asm volatile("stmatrix.sync.aligned.m8n8.x4.shared.b16 [%0], {%1,%2,%3,%4};" ::"r"(a), "r"(r0), "r"(r1), "r"(r2), "r"(r3) : "memory");
}
__device__ __forceinline__ uint32_t pk2(float lo, float hi) { uint32_t r; asm("cvt.rn.bf16x2.f32 %0, %1, %2;" : "=r"(r) : "f"(hi), "f"(lo)); return r; }
__device__ __forceinline__ uint32_t hmul(uint32_t a, uint32_t b) { uint32_t r; asm("mul.rn.bf16x2 %0, %1, %2;" : "=r"(r) : "r"(a), "r"(b)); return r; }
__device__ __forceinline__ uint32_t hadd(uint32_t a, uint32_t b) { uint32_t r; asm("add.rn.bf16x2 %0, %1, %2;" : "=r"(r) : "r"(a), "r"(b)); return r; }
__device__ __forceinline__ uint32_t hmaxabs(uint32_t a, uint32_t b) { uint32_t r; asm("max.xorsign.abs.bf16x2 %0, %1, %2;" : "=r"(r) : "r"(a), "r"(b)); return r; }
__device__ __forceinline__ float ex2(float x) { float r; asm("ex2.approx.ftz.f32 %0, %1;" : "=f"(r) : "f"(x)); return r; }
__device__ __forceinline__ float rcp_fast(float x) { float r; asm("rcp.approx.ftz.f32 %0, %1;" : "=f"(r) : "f"(x)); return r; }
__device__ __forceinline__ uint32_t phi2(float lo, float hi) {
  const float c = 1.4426950408889634f;
  uint32_t r;
  asm("max.bf16x2 %0, %1, %2;" : "=r"(r) : "r"(pk2(lo, hi)), "r"(hadd(pk2(ex2(-fabsf(fmaf(lo, c, -c))), ex2(-fabsf(fmaf(hi, c, -c)))), 0x35863586u)));
  return r;
}
__device__ __forceinline__ bool opaque_true() { uint32_t v; asm volatile("mov.u32 %0, %%nctaid.y;" : "=r"(v)); return v != 0; }
__device__ __forceinline__ int norm_exp(uint32_t (&v)[32], float f0) {
  uint32_t m[4] = {hmaxabs(__float_as_uint(f0) >> 16, v[0]), v[1], v[2], v[3]};
#pragma unroll
  for (int i = 4; i < 32; i++) m[i & 3] = hmaxabs(m[i & 3], v[i]);
  m[0] = hmaxabs(hmaxabs(m[0], m[1]), hmaxabs(m[2], m[3]));
  const int e = min(max((int)(__reduce_max_sync(~0u, max(m[0] & 0x7FFFu, (m[0] >> 16) & 0x7FFFu)) >> 7), 1), 253);
  if (e > 141) {
#pragma unroll
    for (int i = 0; i < 32; i++) v[i] = hmul(v[i], 0x07000700u);
  }
  return e;
}
__device__ __forceinline__ void norm_cvt(uint32_t (&v)[32], float f0, int e) {
  const uint32_t sc = (e > 141 ? 255 - e : 142 - e) * 0x00800080u;
#pragma unroll
  for (int i = 0; i < 32; i++) {
    const uint32_t a = hmul(v[i], sc);
    v[i] = (a & 0x0FFF0FFFu) * 7 + a;
  }
  v[0] = __byte_perm(v[0], __half_as_ushort(__float2half_rn(f0 * __uint_as_float((254 - e) << 23))), 0x3254);
}
__device__ __forceinline__ void poll_ge(const unsigned* p, unsigned target) {
#pragma unroll 1
  for (int n = 0; n < SPIN_LIMIT; n++) {
    unsigned v;
    asm volatile("ld.relaxed.gpu.global.u32 %0, [%1];" : "=r"(v) : "l"(p) : "memory");
    if (__all_sync(~0u, (int)(v - target) >= 0)) { asm volatile("fence.acquire.gpu;" ::: "memory"); return; }
  }
  __trap();
}

__device__ __forceinline__ bool elect_one() {
  uint32_t p;
  asm volatile("{\n.reg .pred p;\nelect.sync _|p, 0xffffffff;\nselp.u32 %0, 1, 0, p;\n}\n" : "=r"(p));
  return p;
}
__device__ __forceinline__ uint4 ld_na4(const void* p) {
  uint4 v;
  asm volatile("ld.global.L1::no_allocate.v4.u32 {%0,%1,%2,%3}, [%4];" : "=r"(v.x), "=r"(v.y), "=r"(v.z), "=r"(v.w) : "l"(p) : "memory");
  return v;
}
__device__ __forceinline__ void st_cg4(void* p, uint4 v) {
  asm volatile("st.global.cg.v4.u32 [%0], {%1,%2,%3,%4};" ::"l"(p), "r"(v.x), "r"(v.y), "r"(v.z), "r"(v.w) : "memory");
}
__device__ __forceinline__ uint32_t mapa(uint32_t a, uint32_t cta) { uint32_t r; asm("mapa.shared::cluster.u32 %0, %1, %2;" : "=r"(r) : "r"(a), "r"(cta)); return r; }
__device__ __forceinline__ void st_async(uint32_t a, uint32_t v, uint32_t bar) {
  asm volatile("st.async.weak.shared::cluster.mbarrier::complete_tx::bytes.b32 [%0], %1, [%2];" ::"r"(a), "r"(v), "r"(bar) : "memory");
}
__device__ __forceinline__ void st_async4(uint32_t a, uint32_t x, uint32_t y, uint32_t z, uint32_t w, uint32_t bar) {
  asm volatile("st.async.weak.shared::cluster.mbarrier::complete_tx::bytes.v4.b32 [%0], {%1,%2,%3,%4}, [%5];" ::"r"(a), "r"(x), "r"(y), "r"(z), "r"(w), "r"(bar) : "memory");
}
__device__ __forceinline__ void tma_q_ld(uint32_t dst, const CUtensorMap* m, int ch, int quarter, int g0, uint32_t bar) {
  asm volatile("cp.async.bulk.tensor.5d.shared::cluster.global.mbarrier::complete_tx::bytes [%0], [%1, {%3, %6, %6, %4, %5}], [%2];"
               ::"r"(dst), "l"(m), "r"(bar), "r"(ch), "r"(8 * quarter), "r"(g0), "r"(0) : "memory");
}
__device__ __forceinline__ void tma_q_st(const CUtensorMap* m, uint32_t src, int ch, int quarter, int g0) {
  asm volatile("cp.async.bulk.tensor.5d.global.shared::cta.bulk_group [%0, {%2, %5, %5, %3, %4}], [%1];"
               ::"l"(m), "r"(src), "r"(ch), "r"(8 * quarter), "r"(g0), "r"(0) : "memory");
}
__device__ __forceinline__ uint4 ld_rlx4(const void* p) {
  uint4 v;
  asm volatile("{\n.reg .b128 t;\n.reg .b64 a, b;\nld.relaxed.gpu.global.b128 t, [%4];\nmov.b128 {a, b}, t;\nmov.b64 {%0, %1}, a;\nmov.b64 {%2, %3}, b;\n}\n"
               : "=r"(v.x), "=r"(v.y), "=r"(v.z), "=r"(v.w) : "l"(p) : "memory");
  return v;
}
__device__ __forceinline__ void ld_stale4(uint4& v, const void* p, uint32_t tag) {
  asm volatile("{\n.reg .b128 t;\n.reg .b64 a, b;\n.reg .b32 x;\n.reg .pred p;\n"
               "lop3.b32 x, %0, %5, 1, 0x28;\nsetp.ne.u32 p, x, 0;\n"
               "mov.b64 a, {%0, %1};\nmov.b64 b, {%2, %3};\nmov.b128 t, {a, b};\n"
               "@p ld.relaxed.gpu.global.b128 t, [%4];\n"
               "mov.b128 {a, b}, t;\nmov.b64 {%0, %1}, a;\nmov.b64 {%2, %3}, b;\n}\n"
               : "+r"(v.x), "+r"(v.y), "+r"(v.z), "+r"(v.w) : "l"(p), "r"(tag) : "memory");
}
__device__ __forceinline__ void st_tag4(void* p, float a, float b, float c, float d, uint32_t tag) {
  asm volatile("{\n.reg .b128 t;\n.reg .b64 a, b;\nmov.b64 a, {%1, %2};\nmov.b64 b, {%3, %4};\nmov.b128 t, {a, b};\nst.relaxed.gpu.global.b128 [%0], t;\n}\n"
               ::"l"(p), "r"((__float_as_uint(a) & ~1u) | tag), "f"(b), "f"(c), "f"(d) : "memory");
}
__device__ __forceinline__ uint32_t stale8(const uint4 (&f)[8], uint32_t tag) {
  uint32_t r[4];
#pragma unroll
  for (int i = 0; i < 4; i++) asm("lop3.b32 %0, %1, %2, %3, 0x7E;" : "=r"(r[i]) : "r"(f[2 * i].x), "r"(f[2 * i + 1].x), "r"(tag));
  asm("lop3.b32 %0, %0, %1, %2, 0xFE;" : "+r"(r[0]) : "r"(r[1]), "r"(r[2]));
  return r[0] | r[3];
}

struct ConvC { uint32_t a1[2][4], wa[2], wb[2], sg; };
__device__ __forceinline__ uint64_t dsc(uint32_t lo, uint32_t hi) { return ((uint64_t)hi << 32) | lo; }
__device__ __forceinline__ uint32_t hfma(uint32_t a, uint32_t b, uint32_t c) { uint32_t r; asm("fma.rn.f16x2 %0, %1, %2, %3;" : "=r"(r) : "r"(a), "r"(b), "r"(c)); return r; }
__device__ __forceinline__ uint32_t hfnma(uint32_t a, uint32_t b, uint32_t c) { uint32_t r; asm("{.reg .b32 n; neg.f16x2 n, %1; fma.rn.f16x2 %0, n, %2, %3;}" : "=r"(r) : "r"(a), "r"(b), "r"(c)); return r; }
__device__ __forceinline__ uint32_t hmul16(uint32_t a, uint32_t b) { uint32_t r; asm("mul.rn.f16x2 %0, %1, %2;" : "=r"(r) : "r"(a), "r"(b)); return r; }
template <int N> __device__ __forceinline__ void keepu(uint32_t (&d)[N]) {
#pragma unroll
  for (int i = 0; i < N; i++) asm volatile("" : "+r"(d[i])::"memory");
}
__device__ __forceinline__ void conv_m1(const ConvC& K, uint32_t (&u)[16], uint32_t l) {
  wg_fence();
  wgmma_hrs_n64<1>(u, K.a1[0][0], K.a1[0][1], K.a1[0][2], K.a1[0][3], dsc(l, 32), 0);
  wgmma_hrs_n64<1>(u, K.a1[1][0], K.a1[1][1], K.a1[1][2], K.a1[1][3], dsc(l + 16, 32), 1);
  wg_commit();
}
__device__ __forceinline__ void conv_s2(const ConvC& K, uint32_t (&u)[16], uint32_t (&Z)[2][8], uint32_t dfl) {
  uint32_t fr[8], fi[8];
#pragma unroll
  for (int c = 0; c < 8; c++) {
    const uint32_t r = hfma(K.wa[c & 1], u[2 * c + 1], u[2 * c]);
    fi[c] = hfma(K.wb[c & 1], r, u[2 * c + 1]);
    fr[c] = hfma(K.wa[c & 1], fi[c], r);
  }
  wg_fence();
#pragma unroll
  for (int p = 0; p < 2; p++) {
    wgmma_hrs_n32<0>(Z[p], fr[4 * p], fr[4 * p + 2], fr[4 * p + 1], fr[4 * p + 3], dsc(dfl, 32), 0);
    wgmma_hrs_n32<0>(Z[p], fi[4 * p], fi[4 * p + 2], fi[4 * p + 1], fi[4 * p + 3], dsc(dfl + 16, 32), 1);
  }
  wg_commit();
}
__device__ __forceinline__ void conv_win(const ConvC& K, const uint32_t (&X)[2][8], uint32_t (&W)[2][8]) {
#pragma unroll
  for (int b = 0; b < 4; b++)
#pragma unroll
    for (int c = 0; c < 2; c++) {
      const uint32_t xr = X[b >> 1][2 * c + (b & 1)], xi = X[b >> 1][4 + 2 * c + (b & 1)];
      const int a = b ? b - 1 : 0;
      W[b >> 1][2 * c + (b & 1)] = b ? hfnma(K.sg, X[a >> 1][4 + 2 * c + (a & 1)], xr) : xr;
      W[b >> 1][4 + 2 * c + (b & 1)] = b ? hfma(K.sg, X[a >> 1][2 * c + (a & 1)], xi) : xi;
    }
}
template <int p>
__device__ __forceinline__ void conv_pw(uint32_t (&X)[2][8], uint32_t (&H)[2][8], uint32_t (&V)[8], uint32_t dil) {
  uint32_t pr[2][2], pi[2][2];
#pragma unroll
  for (int jj = 0; jj < 2; jj++)
#pragma unroll
    for (int c = 0; c < 2; c++) {
      const int j = 2 * p + jj;
      uint32_t sr = 0, si = 0;
#pragma unroll
      for (int a = 0; a <= j; a++) {
        const int b = j - a;
        const uint32_t hr = H[a >> 1][2 * c + (a & 1)], hi = H[a >> 1][4 + 2 * c + (a & 1)];
        const uint32_t xr = X[b >> 1][2 * c + (b & 1)], xi = X[b >> 1][4 + 2 * c + (b & 1)];
        sr = a == 0 ? hmul16(hr, xr) : hfma(hr, xr, sr);
        si = a == 0 ? hmul16(hr, xi) : hfma(hr, xi, si);
        sr = hfnma(hi, xi, sr);
        si = hfma(hi, xr, si);
      }
      pr[jj][c] = sr; pi[jj][c] = si;
    }
  wg_fence();
  wgmma_hrs_n32<0>(V, pr[0][0], pr[1][0], pr[0][1], pr[1][1], dsc(dil, 32), 0);
  wgmma_hrs_n32<0>(V, pi[0][0], pi[1][0], pi[0][1], pi[1][1], dsc(dil + 16, 32), 1);
  wg_commit();
}
template <int p>
__device__ __forceinline__ void conv_it(const ConvC& K, uint32_t (&V)[8], uint32_t vst) {
#pragma unroll
  for (int jj = 0; jj < 2; jj++) {
    uint32_t wr[2], wi[2];
#pragma unroll
    for (int c = 0; c < 2; c++) {
      const uint32_t r = hfnma(K.wa[c], V[4 + 2 * c + jj], V[2 * c + jj]);
      wi[c] = hfnma(K.wb[c], r, V[4 + 2 * c + jj]);
      wr[c] = hfnma(K.wa[c], wi[c], r);
    }
    stsm4(vst + (2 * p + jj) * 2048, wr[0], wr[1], wi[0], wi[1]);
  }
}
__device__ __forceinline__ void conv_m4(uint32_t (&y)[8], uint32_t (&a)[4][4], uint32_t d4l) {
  wg_fence();
  wgmma_hrs_n32<0>(y, a[0][0], a[0][1], a[0][2], a[0][3], dsc(d4l, 64), 0);
#pragma unroll
  for (int s = 1; s < 4; s++) wgmma_hrs_n32<0>(y, a[s][0], a[s][1], a[s][2], a[s][3], dsc(d4l + s * 16, 64), 1);
  wg_commit();
}

struct Params {
  CUtensorMap tmX0, tmW, tmX, tmWo, tmWo1, tmK, tmV, tmQ, tmOA, tmOB;
  const __nv_bfloat16 *shift_k, *h, *D, *x, *w, *wo, *q;
  float *part, *kv;
  uint4* o;
  const uint32_t *thr, *img;
};

__global__ void __cluster_dims__(2, 1, 1) __launch_bounds__(384, 1) fused_kernel(const __grid_constant__ Params P) {
  extern __shared__ __align__(1024) uint8_t smem[];
#define MAP_PF(m) asm volatile("prefetch.tensormap [%0];" ::"l"(&P.m) : "memory")
  if (threadIdx.x == 0) { MAP_PF(tmX0); MAP_PF(tmW); MAP_PF(tmX); }
  const uint32_t sb = __shfl_sync(~0u, smem_u32(smem), 0);
  const uint32_t bars = sb + OFF_BAR;
  const int tid = threadIdx.x, lane = tid & 31;
  const int warp = __shfl_sync(~0u, tid >> 5, 0);
  const int rank = blockIdx.x & 1, pc = blockIdx.x >> 1;
  const unsigned c7 = pc + 6, g7 = (c7 * 37) >> 8;
  const int mb = pc < 4 ? 4 + pc : pc < 36 ? (pc - 4) >> 3 : g7 - 2;
  const int hq = pc < 4 ? 0 : pc < 36 ? (pc - 4) & 7 : 1 + c7 - 7 * g7;
  const int cl = 8 * hq + mb;
  const int hp = 2 * hq + rank;
  const int rb = 2 * mb + (hq >> 2), cb = hq & 3;
#define BAR(i) (bars + 8 * (i))
#define OCNT(rb, hh) ((unsigned*)(P.o + (rb) * OBLK + 16 * 1024 + 8 * (hh)))
#define EPOCH (OCNT(rb, 2)[hp & 7])

  if (tid == 0) { STAMP(0, 0); GSTAMP(0, 30); }
  if (warp == 8) {
    if (elect_one()) {
      mbar_init(BAR(B_FIRST), 1);
      asm volatile("fence.mbarrier_init.release.cluster;" ::: "memory");
      mbar_expect(BAR(B_FIRST), STAGE_BYTES - 16384);
      tma2d(sb, &P.tmX0, 0, mb * 256, BAR(B_FIRST));
      tma2d(sb + 16384, &P.tmX0, 0, mb * 256 + 128, BAR(B_FIRST));
      tma3d(sb + 32768, &P.tmW, hp * 64, 0, 0, BAR(B_FIRST));
      mbar_init(BAR(B_FULL1), 1);
      asm volatile("fence.mbarrier_init.release.cluster;" ::: "memory");
    }
    if (lane == 0) STAMP(3, 21);
  } else if (lane == 0) {
    const int wi = warp - (warp > 8);
#pragma unroll
    for (int r = 0; r < 6; r++)
      if (r < 5 || wi < B_COUNT - 56) mbar_init(BAR(1 + 11 * r + wi), ((uint32_t)(bar_counts(r) >> (4 * wi)) & 15) + 1);
    asm volatile("fence.mbarrier_init.release.cluster;" ::: "memory");
  }
  if (tid == 0) STAMP(2, 6);
  asm volatile("barrier.cluster.arrive.relaxed.aligned;\nbarrier.cluster.wait.aligned;" ::: "memory");
  if (warp == 8 && elect_one()) {
    mbar_expect(BAR(B_FULL1), 16384);
    tma2d_mc(sb + 8192 + rank * 16384, &P.tmX0, 0, mb * 256 + 64 + rank * 128, BAR(B_FULL1));
  }
  if (tid == 256) STAMP(2, 7);

  if (warp < 8) {
    asm volatile("setmaxnreg.inc.sync.aligned.u32 224;");
    const int wg = warp >> 2, w = warp & 3, g = lane >> 2, q = lane & 3, t = tid & 127;
    const bool elect = (t == 0);
    const uint32_t s16 = (sb & 0x3FFFF) >> 4;
    uint32_t pq[2][16], ux[16], uh[16], X[4][2][8], H[4][2][8];
    ConvC K;
    const uint32_t dfl = s16 + (OFF_F2F >> 4) + (8 << 16), dil = s16 + (OFF_F2I >> 4) + (8 << 16), d4l = s16 + (OFF_F4 >> 4) + (8 << 16);
    const uint32_t xl = s16 + (OFF_XT >> 4) + 4 * wg * (XT_STRIDE >> 4) + (8 << 16);
    const uint32_t hl = s16 + (OFF_H >> 4) + wg * 512 + (8 << 16);
    {
      float acc[2][96];
      {
#pragma unroll
        for (int i = 0; i < 192; i++) { acc[i / 96][i % 96] = i % 96 < 64 ? 1.f : 0.f; asm volatile("" : "+f"(acc[i / 96][i % 96])); }
      }
      {
#pragma unroll
        for (int mt = 0; mt < 2; mt++) {
          mbar_wait(BAR(mt ? B_FULL1 : B_FIRST), 0);
          if (mt == 0 && elect) { STAMP(wg, 1); GSTAMP(wg, 26); }
          wg_fence();
#pragma unroll
          for (int ks = 0; ks < 4; ks++)
            wgmma_ss_n192<0, 1>(acc[mt], dsc(s16 + wg * 1024 + mt * 512 + (1 << 16) + ks * 2, SW128), dsc(s16 + 2048 + (512 << 16) + ks * 128, SW128), 1);
        }
        wg_commit();
      }
      int st = 1, ph = 0;
#pragma unroll 1
      for (int kb = 1; kb < 14; kb++) {
        mbar_wait(BAR(B_FULL1 + st), ph);
        if (kb == 8 && elect) { STAMP(wg, 16); GSTAMP(wg, 25); }
        const uint32_t da = s16 + st * (STAGE_BYTES >> 4) + wg * 1024 + (1 << 16);
        const uint32_t db = s16 + st * (STAGE_BYTES >> 4) + 2048 + (512 << 16);
        wg_fence();
#pragma unroll
        for (int ks = 0; ks < 4; ks++) {
          wgmma_ss_n192<0, 1>(acc[0], dsc(da + ks * 2, SW128), dsc(db + ks * 128, SW128), 1);
          wgmma_ss_n192<0, 1>(acc[1], dsc(da + 512 + ks * 2, SW128), dsc(db + ks * 128, SW128), 1);
        }
        wg_commit();
        wg_wait<1>();
        if (t < 2) mbar_arrive_cl(BAR(B_EMPTY1 + (st == 0 ? 2 : st - 1)), t);
        if (++st == 3) { st = 0; ph ^= 1; }
      }
#define TAIL_MMA(mt, stage) do { wg_fence(); _Pragma("unroll") for (int ks = 0; ks < 4; ks++) \
        wgmma_ss_n192<0, 1>(acc[mt], dsc(s16 + (stage) * (STAGE_BYTES >> 4) + wg * 1024 + (mt) * 512 + (1 << 16) + ks * 2, SW128), \
                            dsc(s16 + (stage) * (STAGE_BYTES >> 4) + 2048 + (512 << 16) + ks * 128, SW128), 1); wg_commit(); } while (0)
      mbar_wait(BAR(B_FULL1 + 2), 0);
      TAIL_MMA(0, 2);
      wg_wait<1>();
      if (elect) mbar_arrive(BAR(B_SFREE));
      mbar_wait(BAR(B_FULL1 + 0), 1);
      TAIL_MMA(0, 0);
      TAIL_MMA(1, 2);
      const uint32_t lrow = sb + wg * 16384 + (16 * w + 8 * ((lane >> 3) & 1) + (lane & 7)) * 128 + (((lane >> 4) ^ (lane & 7)) << 4);
#define E1K(mt, i) do { if (opaque_true()) { _Pragma("unroll") for (int j = (i); j < (i) + 2; j++) { \
          const float* a = &acc[mt][32 + 8 * j]; const float* b = a + 32; const uint32_t o = (lrow ^ (j * 32)) + (mt) * 8192; \
          stsm4(o + 2 * STAGE_BYTES, pk2(b[0], b[1]), pk2(b[2], b[3]), pk2(b[4], b[5]), pk2(b[6], b[7])); \
          stsm4(o, phi2(a[0], a[1]), phi2(a[2], a[3]), phi2(a[4], a[5]), phi2(a[6], a[7])); } } } while (0)
#define E1Q(mt) do { if (opaque_true()) { _Pragma("unroll") for (int i = 0; i < 16; i++) pq[mt][i] = phi2(acc[mt][2 * i], acc[mt][2 * i + 1]); } } while (0)
#define LOAD_K() do { const uint4* ct = (const uint4*)P.thr + t; \
        _Pragma("unroll") for (int s = 0; s < 2; s++) { const uint4 u = ld_na4(ct + s * 128); K.a1[s][0] = u.x; K.a1[s][1] = u.y; K.a1[s][2] = u.z; K.a1[s][3] = u.w; } \
        const uint4 u = ld_na4(ct + 2 * 128); K.wa[0] = u.x; K.wa[1] = u.y; K.wb[0] = u.z; K.wb[1] = u.w; \
        K.sg = (lane & 4) ? 0xBC00BC00u : 0x3C003C00u; } while (0)
#define PK_READY(mt) do { fence_async(); __syncwarp(); if (lane == 0) mbar_arrive(BAR(B_PKRDY + (mt))); } while (0)
      wg_wait<1>();
      keep(acc[0]);
      if (elect) STAMP(wg, 18);
      E1K(0, 0);
      TAIL_MMA(1, 0);
      E1K(0, 2);
      if (elect) STAMP(wg, 19);
      PK_READY(0);
      wg_wait<0>();
      keep(acc[1]);
      if (elect) mbar_arrive(BAR(B_G1DONE));
      asm volatile("setmaxnreg.dec.sync.aligned.u32 %0;" ::"n"(RC));
      if (elect) { STAMP(wg, 2); GSTAMP(wg, 27); }
      E1K(1, 0);
      if (elect) STAMP(wg, 20);
      E1K(1, 2);
      if (elect) STAMP(wg, 21);
      PK_READY(1);
      if (elect) STAMP(wg, 3);
      LOAD_K();
      if (elect) STAMP(wg, 4);
      E1Q(0);
      E1Q(1);
      if (elect) STAMP(wg, 17);
      mbar_wait(BAR(B_H), 0);
      conv_m1(K, ux, xl);
      conv_m1(K, uh, hl);
      wg_wait<1>(); keepu(ux);
      if (lane == 0) mbar_arrive_cl(BAR(B_XFREE + 4 * wg), rank ^ 1);
      conv_s2(K, ux, X[0], dfl);
      wg_wait<1>(); keepu(uh);
      conv_s2(K, uh, H[0], dfl);
    }
    if (elect) STAMP(wg, 5);
    float acc[64];
#define G2_MMA(da, db, first) do { wg_fence(); _Pragma("unroll") for (int ks = 0; ks < 4; ks++) \
        wgmma_ss_n128<0, 1>(acc, dsc((da) + ks * 2, SW128), dsc((db) + ks * 128, SW128), ks || !(first)); wg_commit(); } while (0)
    const uint32_t a0 = s16 + wg * 512 + (1 << 16), b0 = s16 + (512 << 16);
    uint32_t cons = mapa(BAR(B_CONS2), t & 1);
    const bool rel = __shfl_sync(~0u, t, lane) < 2;
    {
      uint32_t vst = sb + wg * 8192 + w * 512 + lane * 16, vld = sb + wg * 8192 + w * 2048 + lane * 16;
      uint32_t ya = mapa(sb + OFF_XT + 4 * wg * XT_STRIDE + (2 * rank + (w & 1)) * 1024 + lane * 16, w >> 1);
      const uint32_t ybar = mapa(BAR(B_Y), w >> 1);
      asm volatile("" : "+r"(vst), "+r"(vld), "+r"(ya));
      uint32_t W[2][8], V0[8], V1[8], y[8], a[4][4];
      uint4 ov[4];
      uint4* const ot = P.o + (2 * mb + wg) * OBLK + hq * 1024 + (16 * w + g) * 8 + ((4 * rank + q) ^ g);
#define YOUT(i) do { if ((w >> 1) == rank) { \
          asm volatile("st.shared.v4.b32 [%0], {%1,%2,%3,%4};" ::"r"(ya + (i) * XT_STRIDE), "r"(y[0]), "r"(y[1]), "r"(y[2]), "r"(y[3]) : "memory"); \
          asm volatile("st.shared.v4.b32 [%0], {%1,%2,%3,%4};" ::"r"(ya + (i) * XT_STRIDE + 512), "r"(y[4]), "r"(y[5]), "r"(y[6]), "r"(y[7]) : "memory"); \
        } else { \
          mbar_wait(BAR(B_XFREE + 4 * wg + (i)), 0); \
          st_async4(ya + (i) * XT_STRIDE, y[0], y[1], y[2], y[3], ybar); \
          st_async4(ya + (i) * XT_STRIDE + 512, y[4], y[5], y[6], y[7], ybar); } } while (0)
      auto ocalc = [&](const int hh) {
        if (hh == 0) {
          if (elect) STAMP(wg, 8);
          mbar_wait(BAR(B_KV), 0);
          if (elect) STAMP(wg, 9);
        } else mbar_wait(BAR(B_KV1), 0);
        float oa[2][20];
        wg_fence();
#pragma unroll
        for (int m = 0; m < 4; m++) {
          const uint32_t* p = &pq[m & 1][8 * hh + 4 * (m >> 1)];
          wgmma_rs_n40<1>(oa[m & 1], p[0], p[1], p[2], p[3], dsc(s16 + (OFF_KVB >> 4) + hh * 160 + (m >> 1) * 16 + (8 << 16), 32), m >> 1);
        }
        wg_commit();
        wg_wait<0>();
#pragma unroll
        for (int mt = 0; mt < 2; mt++) {
          float (&o)[20] = oa[mt];
          keep(o);
          const uint32_t den = hadd(pk2(o[16], o[18]), 0x35863586u);
#pragma unroll
          for (int r = 0; r < 2; r++) {
            const float ri = rcp_fast(__uint_as_float(r ? (den & 0xFFFF0000u) : (den << 16)));
            uint4 u;
            u.x = pk2(o[2 * r] * ri, o[2 * r + 1] * ri);
            u.y = pk2(o[4 + 2 * r] * ri, o[5 + 2 * r] * ri);
            u.z = pk2(o[8 + 2 * r] * ri, o[9 + 2 * r] * ri);
            u.w = pk2(o[12 + 2 * r] * ri, o[13 + 2 * r] * ri);
            if (hh == 0) st_cg4(ot + (64 * mt + 8 * r) * 8, u); else ov[2 * mt + r] = u;
          }
        }
        if (hh == 0) {
          __syncwarp();
          if (lane == 0) mbar_arrive(BAR(B_ODONE));
          if (elect) STAMP(wg, 10);
        }
      };
      auto trickle = [&](const int qs) {
        const int m = qs - 2 * (OCH + O1D) - (TRICK - 1);
        if (m >= 0 && m < 4) {
          st_cg4(ot + 8 * 1024 + (64 * (m >> 1) + 8 * (m & 1)) * 8, ov[m]);
          if (m == 3) { __syncwarp(); if (lane == 0) mbar_arrive(BAR(B_ODONE1)); }
        }
      };
#pragma unroll
      for (int i = 0; i < 4; i++) {
        const bool nx = i < 3;
        const int n = nx ? i + 1 : i;
        const uint32_t vo = (i & 1) ? OFF_H + (i >> 1) * 16384 : OFF_VP;
        if (2 * i == OCH) ocalc(0);
        if (2 * i == OCH + O1D) ocalc(1);
        if (nx) {
          conv_m1(K, ux, xl + n * (XT_STRIDE >> 4));
          conv_m1(K, uh, hl + (n >> 1) * 1024 + (n & 1) * 256);
        }
        if (2 * i != OCH && 2 * i != OCH + O1D) { if (nx) { if (i > 0) wg_wait<3>(); else wg_wait<2>(); } else wg_wait<1>(); }
        keepu(X[i][0]); keepu(X[i][1]); keepu(H[i][0]); keepu(H[i][1]);
        conv_win(K, X[i], W);
        trickle(4 * i);
        conv_pw<0>(W, H[i], V0, dil);
        conv_pw<1>(W, H[i], V1, dil);
        trickle(4 * i + 1);
        wg_wait<2>();
        if (i > 0) { keepu(y); YOUT(i - 1); }
        if (2 * i + 1 == OCH) ocalc(0);
        if (2 * i + 1 == OCH + O1D) ocalc(1);
        if (nx) {
          keepu(ux); keepu(uh);
          if (lane == 0) mbar_arrive_cl(BAR(B_XFREE + 4 * wg + n), rank ^ 1);
          conv_s2(K, ux, X[n], dfl);
          wg_wait<1>();
        } else wg_wait<0>();
        keepu(V0); keepu(V1);
        trickle(4 * i + 2);
        if (i == 0) mbar_wait(BAR(B_H2), 0);
        conv_it<0>(K, V0, vst + vo);
        conv_it<1>(K, V1, vst + vo);
        if (i == 3) { mbar_wait(BAR(B_FULL2), 0); G2_MMA(a0 + (SLOT_A & 15) * 1024, b0 + (SLOT_B & 15) * 1024, true); }
        bar_sync(1 + wg);
#pragma unroll
        for (int s = 0; s < 4; s++) ldsm4t(a[s], vld + vo + s * 512);
        if (nx) conv_s2(K, uh, H[n], dfl);
        conv_m4(y, a, d4l);
        trickle(4 * i + 3);
        if (i > 0 && lane < 2) mbar_arrive_cl(BAR(B_AFREE + i - 1), lane);
        if (elect && i < 3) STAMP(wg, i < 2 ? 6 + i : 9 + i);
      }
      wg_wait<0>();
      keepu(y);
      if (rel) asm volatile("mbarrier.arrive.shared::cluster.b64 _, [%0];" ::"r"(cons) : "memory");
      YOUT(3);
      __syncwarp();
      if (lane == 0) mbar_arrive(BAR(B_Y));
      if (elect) STAMP(wg, 12);
    }
    {
      uint64_t ta = SLOT_A >> 4, tb = SLOT_B >> 4;
      uint32_t da = a0 + ((uint32_t)ta & 15) * 1024, db = b0 + ((uint32_t)tb & 15) * 1024, fb = BAR(B_FULL2 + 1);
#pragma unroll 1
      for (int kb = 1; kb < HOLD2; kb++) {
        mbar_wait(fb, 0);
        G2_MMA(da, db, false);
        ta >>= 4; tb >>= 4;
        da = a0 + ((uint32_t)ta & 15) * 1024; db = b0 + ((uint32_t)tb & 15) * 1024; fb += 8;
        asm volatile("" : "+r"(da), "+r"(db));
        wg_wait<1>();
        if (kb > 1 && kb < 12 && rel) asm volatile("mbarrier.arrive.shared::cluster.b64 _, [%0];" ::"r"(cons) : "memory");
        cons += 8;
      }
#pragma unroll
      for (int kb = HOLD2; kb < 16; kb++) {
        if (wg == 1) mbar_wait(BAR(B_FULL2 + kb), 0);
        else if (kb == HOLD2) asm volatile("bar.sync 3, 256;" ::: "memory");
        G2_MMA(a0 + ((SLOT_A >> (4 * kb)) & 15) * 1024, b0 + ((SLOT_B >> (4 * kb)) & 15) * 1024, false);
      }
      if (wg == 1) asm volatile("bar.arrive 3, 256;" ::: "memory");
      const uint32_t stg = sb + wg * 8192 + w * 2048, so0 = ((SLOT_A >> 56) & 15) * 16384, so1 = ((SLOT_A >> 60) & 15) * 16384;
      const uint32_t lrow = stg + (8 * ((lane >> 3) & 1) + (lane & 7)) * 128 + (((lane >> 4) ^ (lane & 7)) << 4);
      const int col = 1024 + 256 * cb + 128 * rank, row = 128 * rb + 64 * wg + 16 * w;
      wg_wait<0>();
      keep(acc);
      if (elect) { STAMP(wg, 14); GSTAMP(wg, 29); }
#pragma unroll
      for (int cp = 0; cp < 8; cp++) {
        const float* a = &acc[8 * cp];
        stsm4((lrow ^ ((cp & 3) * 32)) + (cp >> 2 ? so1 : so0), pk2(a[0], a[1]), pk2(a[2], a[3]), pk2(a[4], a[5]), pk2(a[6], a[7]));
        if ((cp & 3) == 3) {
          fence_async();
          __syncwarp();
          if (elect_one()) tma2d_st(&P.tmOB, stg + (cp >> 2 ? so1 : so0), col + (cp >> 2) * 64, row);
        }
      }
      asm volatile("cp.async.bulk.commit_group;\ncp.async.bulk.wait_group.read 0;" ::: "memory");
      if (elect) {
        STAMP(wg, 15); GSTAMP(wg, 31); PDUMP(wg); if (wg == 0) PDUMP(2);
      }
    }
  } else {
    asm volatile("setmaxnreg.dec.sync.aligned.u32 56;");
    const int hw = warp - 9, g = lane >> 2, q = lane & 3;
#define sbar (bars + 8 * (B_STG - 18) + 16 * warp)
    if (warp == 8) {
      if (D1) __nanosleep(D1);
      int st = 1, pp = 1;
      const uint8_t* pfx = (const uint8_t*)P.x + (mb * 256 + hp * 16 + (lane & 15)) * 2048;
      const uint8_t* pfw = (const uint8_t*)P.w + (mb * 8 + (lane & 7)) * 6144 + (lane >> 3) * 2048 + hp * 128;
#pragma unroll 1
      for (int kb = 1; kb < 16; kb++) {
        if (kb >= 3) mbar_wait(BAR(B_EMPTY1 + st), pp);
        const uint32_t sa = sb + st * STAGE_BYTES;
        if (elect_one()) {
          mbar_expect(BAR(B_FULL1 + st), STAGE_BYTES);
          tma2d_mc(sa + rank * 16384, &P.tmX, kb * 64, mb * 256 + rank * 128, BAR(B_FULL1 + st));
          tma3d(sa + 32768, &P.tmW, hp * 64, kb * 64, 0, BAR(B_FULL1 + st));
        }
        if (kb == 1 && lane == 0) STAMP(2, 24);
        if (PFD && kb >= 2) {
#pragma unroll 1
          for (int j = kb == 2 ? 3 : kb + PFD; j <= kb + PFD && j < 16; j++) {
            if (lane < 16) asm volatile("prefetch.global.L2 [%0];" ::"l"(pfx + j * 128));
            if (lane < 24) asm volatile("prefetch.global.L2 [%0];" ::"l"(pfw + j * (64 * 6144)));
          }
          if (kb >= QPF && kb < QPF + 8) asm volatile("prefetch.global.L2 [%0];" ::"l"((const uint8_t*)P.q + (blockIdx.x * 256 + (kb - QPF) * 16 + (lane & 16) * 8 + (lane & 15)) * 128));
          if (kb >= 4)
            asm volatile("prefetch.global.L2 [%0];" ::"l"(kb < 12 ? (const uint8_t*)P.h + ((2 * cl + rank) * 256 + (kb - 4) * 32 + lane) * 128
                                                                  : (const uint8_t*)P.wo + (blockIdx.x * 128 + (kb - 12) * 32 + lane) * 128));
        }
        if (++st == 3) { st = 0; pp ^= 1; }
      }
      if (elect_one()) { MAP_PF(tmWo); MAP_PF(tmWo1); }
      if (lane == 0) STAMP(2, 1);
    } else {
      {
        const uint32_t clk0 = __shfl_sync(~0u, (uint32_t)clock(), 0), stg = sb + OFF_STG + hw * STG_STRIDE;
        const unsigned epoch = __shfl_sync(~0u, EPOCH, 0);
        const uint32_t tag = ~epoch & 1;
        uint32_t tap[2][4];
#pragma unroll
        for (int cg = 0; cg < 2; cg++) {
          const uint2 u = __ldg((const uint2*)(P.shift_k + (16 * cl + 8 * cg + g) * 4));
          tap[cg][0] = __byte_perm(u.x, 0, 0x1010); tap[cg][1] = __byte_perm(u.x, 0, 0x3232);
          tap[cg][2] = __byte_perm(u.y, 0, 0x1010); tap[cg][3] = __byte_perm(u.y, 0, 0x3232);
        }
        if (hw == 0 && lane < 8) *(float*)(smem + OFF_D + 4 * lane) = __bfloat162float(P.D[16 * cl + 8 * rank + lane]);
        if (hw == 1 && lane < 24) asm volatile("prefetch.global.L2 [%0];" ::"l"(P.thr + (lane + 24 * rank) * 32));
        if (hw == 0 && elect_one()) {
          *(volatile unsigned*)(smem + OFF_EPOCH) = epoch;
          mbar_expect(BAR(B_XRAW), 16384);
          mbar_expect(BAR(B_Y), 16384 + 64);
        }
#pragma unroll 1
        for (int i = hw * 32 + lane; i < 528; i += 96) st_tag4(P.part + (hp * 8 + mb) * 2176 + 4 * i, 0.f, 0.f, 0.f, 0.f, tag ^ 1);
        if (hw < 2 || lane < 2) st_tag4(P.kv + hp * 2176 + (4 * (hw < 2 ? 64 * mb + 32 * hw + lane : 512 + 8 * (mb & 1) + (mb & 6) + lane)), 0.f, 0.f, 0.f, 0.f, tag ^ 1);
        if (lane == 0) STAMP(3, hw);
        const uint32_t xo = sb + OFF_XT + g * XT_STRIDE + rank * 2048 + q * 4;
        const int krow = 8 + (lane & 7) - (lane >> 3);
        const uint32_t ka = stg + krow * 32 + ((krow & 4) << 2), va = stg + 2304 + lane * 32 + ((lane & 4) << 2);
        int ph = 0, b = 0;
#pragma unroll 1
        for (int ci = hw - 3; ci < 16; ci += 3) {
          const uint32_t bo = b ? OFF_F2F - OFF_STG : 0, bn = b ? 0 : OFF_F2F - OFF_STG;
          if (ci + 3 < 16) {
            while (__any_sync(~0u, (uint32_t)clock() - clk0 < HSTART + (ci + 3) * PACE)) __nanosleep(64);
            if (elect_one()) {
              mbar_expect(sbar + 8 * (b ^ 1), 2304 + 2048);
              tma2d(stg + bn, &P.tmK, 16 * cl, 1024 * rank + 64 * (ci + 3) - 8, sbar + 8 * (b ^ 1));
              tma2d(stg + bn + 2304, &P.tmV, 16 * cl, 1024 * rank + 64 * (ci + 3), sbar + 8 * (b ^ 1));
            }
          }
          if (ci >= 0) {
            mbar_wait(sbar + 8 * b, (ph >> b) & 1);
            ph ^= 1 << b;
#pragma unroll 1
            for (int grp = 0; grp < 2; grp++) {
#pragma unroll
              for (int cg = 0; cg < 2; cg++) {
                const uint32_t dst = mapa(xo + (ci >> 3) * 1024 + ((ci & 7) * 4 + 2 * grp) * 16, cg), xbar = mapa(BAR(B_XRAW), cg);
                uint32_t vv[4], kk[4][4];
                ldsm4t(vv, (va ^ (cg * 16)) + bo + grp * 1024);
#pragma unroll
                for (int rg = 0; rg < 4; rg++) ldsm4t(kk[rg], (ka ^ (cg * 16)) + bo + grp * 1024 + rg * 256);
#pragma unroll
                for (int rg = 0; rg < 4; rg++)
                  vv[rg] = hmul(hadd(hadd(hadd(hmul(kk[rg][3], tap[cg][3]), hmul(kk[rg][2], tap[cg][2])), hmul(kk[rg][1], tap[cg][1])), hmul(kk[rg][0], tap[cg][0])), vv[rg]);
                if (cg == rank) {
#pragma unroll
                  for (int rg = 0; rg < 4; rg++) asm volatile("st.shared.b32 [%0], %1;" ::"r"(dst + (rg & 1) * 512 + (rg >> 1) * 16), "r"(vv[rg]) : "memory");
                } else {
#pragma unroll
                  for (int rg = 0; rg < 4; rg++) st_async(dst + (rg & 1) * 512 + (rg >> 1) * 16, vv[rg], xbar);
                }
              }
            }
          }
          b ^= 1;
        }
      }
      if (lane == 0 && hw == 0) STAMP(3, 3);
      asm volatile("bar.sync 4, 96;" ::: "memory");
      if (hw == 0 && elect_one()) { mbar_expect(BAR(B_XT), 10240); bulk_ld(sb + OFF_F2F, P.img, 10240, BAR(B_XT)); }
      mbar_wait(BAR(B_XRAW), 0);
    }
    int e1 = 0;
#pragma unroll 1
    for (int n = hw < 0 ? 3 : 0; n < 4; n++) {
      const bool isH = n >= 3;
      const int c = isH ? (warp & 1) + 2 * (warp & 2) : hw + 3 * n;
      if (c < 8) {
        int ln;
        asm volatile("mov.u32 %0, %%laneid;" : "=r"(ln));
        uint8_t* dst = smem + (isH ? OFF_H + (c & 2) * 8192 + (c >> 2) * 8192 + (c & 1) * 4096 : OFF_XT + c * XT_STRIDE) + ((ln >> 4) * 512 + (ln & 15) * 16);
        const uint8_t* src0 = isH ? (const uint8_t*)P.h + (16 * cl + 8 * rank + c) * 4096 + ((ln & 15) * 32 + (ln & 16)) : dst;
        const uint8_t* src1 = src0 + (isH ? 512 : 256);
        uint32_t v[32];
#pragma unroll
        for (int i = 0; i < 8; i++) {
          const uint4 u = *(const uint4*)(((i & 1) ? src1 : src0) + (i >> 1) * 1024);
          v[4 * i] = u.x; v[4 * i + 1] = u.y; v[4 * i + 2] = u.z; v[4 * i + 3] = u.w;
        }
        if (isH) mbar_wait(BAR(B_XT), 0);
        const float f0 = __uint_as_float(v[0] << 16) + ((isH && ln == 0) ? *(const float*)(smem + OFF_D + 4 * c) : 0.f);
        const int e = norm_exp(v, f0);
        norm_cvt(v, f0, e);
        if (isH) mbar_wait(BAR(B_SFREE), 0);
        else if (ln == 0) smem[OFF_EX + c] = e;
        e1 = e;
#pragma unroll
        for (int i = 0; i < 8; i++)
          *(uint4*)(dst + (i >> 1) * 1024 + (i & 1) * 256) = make_uint4(v[4 * i], v[4 * i + 1], v[4 * i + 2], v[4 * i + 3]);
        if (n < 2 && elect_one()) {
          if (n == 0) mbar_expect(sbar, 4096);
          tma_q_ld(sb + OFF_STG + 2048 * c, &P.tmQ, 16 * cl, 2 * rank, c, sbar);
        }
      }
      if (n >= 2) {
        fence_async();
        __syncwarp();
        if (lane == 0) { mbar_arrive(BAR(isH ? B_H : B_XT)); STAMP(3, (isH ? 17 : 13) + hw); }
      }
    }
#define SLOT(tab, kb) (sb + ((uint32_t)((tab) >> (4 * (kb))) & 15) * 16384)
#define KT(kb) ((kb) == 0 ? hq : (kb) == hq ? 0 : (kb))
#define LOAD_B(kb) tma4d(SLOT(SLOT_B, kb), &P.tmWo, 0, ((kb) >> 3) * 32, 2 * (KT(kb) & 7), 4 * cb + 2 * rank, BAR(B_FULL2 + (kb)))
#define LOAD_A(kb) bulk_ld_mc(SLOT(SLOT_A, kb) + rank * 8192, P.o + rb * OBLK + KT(kb) * 1024 + rank * 512, 8192, BAR(B_FULL2 + (kb)))
    mbar_wait(BAR(B_G1DONE), 0);
    asm volatile("setmaxnreg.inc.sync.aligned.u32 %0;" ::"n"(504 - 2 * RC));
    {
    int tid;
    asm volatile("mov.u32 %0, %%tid.x;" : "=r"(tid));
    const int lane = tid & 31, g = lane >> 2, q = lane & 3;
    const unsigned epoch = *(volatile unsigned*)(smem + OFF_EPOCH);
    const uint32_t tag = ~epoch & 1;
    const int pi = hw < 2 ? 64 * mb - 288 + tid : 512 + 8 * (mb & 1) + (mb & 6) + (lane & 1);
    const float* psrc = P.part + hp * 8 * 2176 + 4 * pi;
    uint4 f[8];
    {
      const uint32_t s16 = (sb & 0x3FFFF) >> 4;
      const int t = tid & 127, c = 2 + (warp & 1) + 2 * (warp & 2);
      const uint4* hp4 = (const uint4*)(P.h + (16 * cl + 8 * rank + c) * 2048) + ((lane & 15) * 2 + (lane >> 4));
      uint32_t v[32];
#pragma unroll
      for (int i = 0; i < 8; i++) { const uint4 u = ld_na4(hp4 + i * 32); v[4 * i] = u.x; v[4 * i + 1] = u.y; v[4 * i + 2] = u.z; v[4 * i + 3] = u.w; }
      float kva[36];
#pragma unroll
      for (int mt = 0; mt < 2; mt++) {
        mbar_wait(BAR(B_PKRDY + mt), 0);
        wg_fence();
#pragma unroll
        for (int ks = 0; ks < 8; ks++) {
          const uint32_t o = (ks >> 2) * 1024 + mt * 512 + (ks & 3) * 128, vb = (2 * STAGE_BYTES >> 4) + o;
          wgmma_ss_n72<1, 1>(kva, dsc(s16 + o + (1 << 16), SW128), dsc(s16 + vb + (((OFF_ONES >> 4) - vb) << 16), SW128), (mt | ks) != 0);
        }
        wg_commit();
        if (mt == 0 && hw < 0) {
          if (elect_one()) {
#pragma unroll
            for (int kb = 0; kb < BEARLY; kb++) { mbar_expect(BAR(B_FULL2 + kb), 16384); LOAD_B(kb); }
          }
        }
      }
      float* pdst = P.part + (hp * 8 + mb) * 2176 + t * 4;
      float* zdst = P.part + (hp * 8 + mb) * 2176 + 2048 + (t >> 1);
      asm volatile("" : "+l"(pdst), "+l"(zdst));
      wg_wait<0>();
      keep(kva);
      if (hw < 1) {
#pragma unroll
        for (int c = 0; c < 4; c++) st_tag4(pdst + c * 512, kva[4 * c], kva[4 * c + 1], kva[4 * c + 2], kva[4 * c + 3], tag);
      } else {
#pragma unroll
        for (int c = 4; c < 8; c++) st_tag4(pdst + (c - 4) * 512, kva[4 * c], kva[4 * c + 1], kva[4 * c + 2], kva[4 * c + 3], tag);
      }
      const float z2 = __shfl_down_sync(~0u, kva[32], 4), z3 = __shfl_down_sync(~0u, kva[34], 4);
      if (!(lane & 7)) st_tag4(zdst, kva[32], kva[34], z2, z3, tag);
      if (lane == 0) mbar_arrive(BAR(B_PKFREE));
      const uint32_t cst = clock();
      if (hw == 0 && lane == 0) STAMP(3, 24);
      const float f0 = __uint_as_float(v[0] << 16) + (lane == 0 ? *(const float*)(smem + OFF_D + 4 * c) : 0.f);
      const int e = norm_exp(v, f0);
      norm_cvt(v, f0, e);
      if (hw >= 0) {
        while (__any_sync(~0u, (uint32_t)clock() - cst < PD1)) __nanosleep(20);
        if (hw == 0 && lane == 0) STAMP(3, 20);
#pragma unroll
        for (int p = 0; p < 8; p++) f[p] = ld_rlx4(psrc + p * 2176);
      }
      uint8_t* dst = smem + OFF_H + 16384 + (warp & 3) * 4096 + (lane >> 4) * 512 + (lane & 15) * 16;
#pragma unroll
      for (int i = 0; i < 8; i++)
        *(uint4*)(dst + (i >> 1) * 1024 + (i & 1) * 256) = make_uint4(v[4 * i], v[4 * i + 1], v[4 * i + 2], v[4 * i + 3]);
      if (lane < 4) {
        const int cc = c - (lane & 2);
        st_async(mapa(sb + OFF_SCALE + (8 * rank + cc) * 4, lane & 1), min(max(((lane & 2) ? e1 : e) + smem[OFF_EX + cc] - 124, 1), 254) << 23, mapa(BAR(B_Y), lane & 1));
      }
    }
#define H2_READY() do { fence_async(); __syncwarp(); if (lane == 0) mbar_arrive(BAR(B_H2)); } while (0)
    if (warp == 8) {
      H2_READY();
      mbar_wait(BAR(B_PKFREE), 0);
      {
        const uint32_t c0 = clock();
#pragma unroll 1
        for (int i = 0; i < 2 * NPRE - 2 * BEARLY; i++) {
          const int kb = (i >> 1) + BEARLY;
          while (__any_sync(~0u, (uint32_t)clock() - c0 < i * BPACE)) __nanosleep(32);
          if (elect_one()) {
            if (!(i & 1)) mbar_expect(BAR(B_FULL2 + kb), 16384);
            tma4d(SLOT(SLOT_B, kb) + (i & 1) * 8192, &P.tmWo1, 0, 0, 2 * KT(kb), 4 * cb + 2 * rank + (i & 1), BAR(B_FULL2 + kb));
            if (i == 0) mbar_expect(BAR(B_Q), 8192);
            if (i < 4) tma_q_ld(sb + OFF_SPARE + 2048 * i, &P.tmQ, 16 * cl, 2 * rank + (i >> 1), (i + 6) & 7, BAR(B_Q));
          }
        }
      }
      if (elect_one()) { MAP_PF(tmOA); MAP_PF(tmOB); }
      if (lane == 0) STAMP(2, 2);
      {
        if (elect_one()) mbar_expect(BAR(B_FULL2), 16384);
        mbar_wait(BAR(B_OLOC), 0);
        asm volatile("fence.acquire.cluster;\nfence.proxy.async.global;" ::: "memory");
        if (elect_one()) LOAD_A(0);
      }
      mbar_wait(BAR(B_AFREE), 0);
      if (elect_one()) mbar_expect(BAR(B_FULL2 + 1), 16384);
      {
        const uint32_t dst = SLOT(SLOT_A, 1) + rank * 8192;
        const uint4* src = P.o + rb * OBLK + KT(1) * 1024 + rank * 512;
        poll_ge(OCNT(rb, 0), 16 * (epoch + 1));
        asm volatile("fence.proxy.async.global;" ::: "memory");
        if (lane == 0) STAMP(2, 3);
        if (elect_one()) bulk_ld_mc(dst, src, 8192, BAR(B_FULL2 + 1));
        if (lane == 0) STAMP(3, 23);
      }
#pragma unroll 1
      for (int kb = 2; kb < NPRE; kb++) {
        mbar_wait(BAR(kb < 4 ? B_AFREE + kb - 1 : B_CONS2), 0);
        if (elect_one()) { mbar_expect(BAR(B_FULL2 + kb), 16384); LOAD_A(kb); }
      }
#pragma unroll 1
      for (int kb = NPRE; kb < 16; kb++) {
        mbar_wait(BAR(B_CONS2 + kb - 5), 0);
        if (kb == 8) mbar_wait(BAR(B_O1RDY), 0);
        if (elect_one()) { mbar_expect(BAR(B_FULL2 + kb), 32768); LOAD_A(kb); LOAD_B(kb); }
      }
      if (lane == 0) { EPOCH = epoch + 1; STAMP(2, 5); }
    } else {
      {
#pragma unroll 1
        for (int n = 0; __any_sync(~0u, stale8(f, tag) & 1); n++) {
#pragma unroll
          for (int p = 0; p < 8; p++) ld_stale4(f[p], psrc + p * 2176, tag);
          if (n > SPIN_LIMIT) __trap();
        }
        float s0 = 0.f, s1 = 0.f, s2 = 0.f, s3 = 0.f;
#pragma unroll
        for (int p = 0; p < 8; p++) { s0 += __uint_as_float(f[p].x); s1 += __uint_as_float(f[p].y); s2 += __uint_as_float(f[p].z); s3 += __uint_as_float(f[p].w); }
        if (hw < 2 || lane < 2) st_tag4(P.kv + hp * 2176 + (4 * pi), s0, s1, s2, s3, tag);
      }
      const uint32_t cs2 = clock();
      if (lane == 0 && hw == 0) STAMP(3, 8);
      H2_READY();
      if (hw == 2) {
        unsigned* cnt = OCNT(2 * mb + lane, 0);
#pragma unroll 1
        for (int hh = 0; hh < 2; hh++) {
          mbar_wait(BAR(hh ? B_ODONE1 : B_ODONE), 0);
          if (lane < 2) asm volatile("red.release.gpu.global.add.u32 [%0], 1;" ::"l"(cnt) : "memory");
          if (hh == 0 && lane < 2) mbar_arrive_cl(BAR(B_OLOC), lane);
          cnt += 32;
          if (lane == 0) STAMP(3, hh ? 6 : 7);
        }
        poll_ge(OCNT(rb, 1), 16 * (epoch + 1));
        asm volatile("fence.proxy.async.global;" ::: "memory");
        if (lane == 0) { mbar_arrive(BAR(B_O1RDY)); STAMP(2, 4); }
        __syncwarp();
      } else {
        const int t = tid - 288;
        const float* src = P.kv + hp * 2176 + 4 * (t + 32 * hw);
        const float* zsrc = P.kv + hp * 2176 + (2048 + (t & 48) + 2 * (lane & 6));
        mbar_wait(BAR(B_PKFREE), 0);
        while (__any_sync(~0u, (uint32_t)clock() - cs2 < PD2)) __nanosleep(20);
        uint4 zp = ld_rlx4(zsrc);
#pragma unroll
        for (int p = 0; p < 8; p++) f[p] = ld_rlx4(src + 4 * ((p & 3) * 128 + (p >> 2) * 32));
        if (!opaque_true()) __trap();
#pragma unroll 1
        for (int n = 0; __any_sync(~0u, (stale8(f, tag) | (zp.x ^ tag)) & 1); n++) {
          ld_stale4(zp, zsrc, tag);
#pragma unroll
          for (int p = 0; p < 8; p++) ld_stale4(f[p], src + 4 * ((p & 3) * 128 + (p >> 2) * 32), tag);
          if (n > SPIN_LIMIT) __trap();
        }
#define PK2U(a, b) pk2(__uint_as_float(a), __uint_as_float(b))
        const uint32_t zf = (lane & 1) ? ((lane & 8) ? zp.w : zp.z) : ((lane & 8) ? zp.y : zp.x);
        const uint32_t zz = PK2U(zf, zf);
        *(uint4*)(smem + OFF_KVB + hw * 2560 + 2048 + lane * 16) = make_uint4(zz, zz, zz, zz);
#pragma unroll
        for (int hh = 0; hh < 2; hh++) {
          const uint4* ff = &f[4 * hh];
          uint8_t* dst = smem + OFF_KVB + hw * 2560 + q * 512 + (16 * hh + g) * 16;
          *(uint4*)dst = make_uint4(PK2U(ff[0].x, ff[0].y), PK2U(ff[1].x, ff[1].y), PK2U(ff[2].x, ff[2].y), PK2U(ff[3].x, ff[3].y));
          *(uint4*)(dst + 128) = make_uint4(PK2U(ff[0].z, ff[0].w), PK2U(ff[1].z, ff[1].w), PK2U(ff[2].z, ff[2].w), PK2U(ff[3].z, ff[3].w));
        }
        fence_async();
        __syncwarp();
        if (lane == 0) { mbar_arrive(BAR(hw ? B_KV1 : B_KV)); if (hw == 0) STAMP(3, 9); }
      }
#define QBUF(ci) (sb + 2048 * (ci) + ((ci) < 6 ? OFF_STG : (ci) < 10 ? OFF_SPARE - 6 * 2048 : OFF_F2F - 10 * 2048))
      mbar_wait(BAR(B_Y), 0);
      if (elect_one()) {
        mbar_expect(sbar + 8, 4096);
#pragma unroll 1
        for (int ci = hw ? hw + 9 : 12; ci < 16; ci += 3) tma_q_ld(QBUF(ci), &P.tmQ, 16 * cl, 2 * rank + 1, ci & 7, sbar + 8);
      }
      mbar_wait(BAR(B_Q), 0);
      mbar_wait(sbar, hw == 0);
      {
        const uint2 f0 = *(const uint2*)(smem + OFF_SCALE + 8 * q), f1 = *(const uint2*)(smem + OFF_SCALE + 32 + 8 * q);
        const uint32_t sc0 = __byte_perm(f0.x, f0.y, 0x7632), sc1 = __byte_perm(f1.x, f1.y, 0x7632);
        const uint32_t yl = sb + OFF_XT + (lane & 7) * XT_STRIDE + (lane >> 3) * 16;
#pragma unroll 1
        for (int ci = hw; ci < 16; ci += 3) {
          const uint32_t qb = QBUF(ci);
          if (ci >= 10) mbar_wait(sbar + 8, 1);
          uint32_t yy[4][4], qq[4][4];
          const uint32_t qa = qb + ((lane & 25) + (lane & 2) * 2 + ((lane >> 1) & 2)) * 32 + ((lane & 2) << 3);
#pragma unroll
          for (int u = 0; u < 4; u++) {
            ldsm4t(yy[u], yl + (u & 1) * 2048 + (ci >> 3) * 1024 + (u >> 1) * 512 + (ci & 7) * 64);
            ldsm4(qq[u], (qa ^ ((u & 1) * 16)) + (u >> 1) * 1024);
          }
          if (!opaque_true()) __trap();
#pragma unroll
          for (int u = 0; u < 4; u++) {
#pragma unroll
            for (int m = 0; m < 4; m++) {
              const float2 f = __half22float2(*(const __half2*)&yy[u][m]);
              qq[u][m] = hmul(qq[u][m], hmul(pk2(f.x, f.y), (u & 1) ? sc1 : sc0));
            }
            stsm4((qa ^ ((u & 1) * 16)) + (u >> 1) * 1024, qq[u][0], qq[u][1], qq[u][2], qq[u][3]);
          }
          fence_async();
          __syncwarp();
          if (elect_one()) tma_q_st(&P.tmOA, qb, 16 * cl, 2 * rank + (ci >> 3), ci & 7);
        }
        asm volatile("cp.async.bulk.commit_group;\ncp.async.bulk.wait_group.read 0;" ::: "memory");
      }
      if (lane == 0) STAMP(3, 10 + hw);
    }
    }
  }
}

typedef CUresult (*EncodeFn)(CUtensorMap*, CUtensorMapDataType, cuuint32_t, void*, const cuuint64_t*, const cuuint64_t*,
                             const cuuint32_t*, const cuuint32_t*, CUtensorMapInterleave, CUtensorMapSwizzle,
                             CUtensorMapL2promotion, CUtensorMapFloatOOBfill);

static void enc(EncodeFn fn, CUtensorMap* m, const void* p, int rank, const cuuint64_t* dims, const cuuint64_t* strides,
                const cuuint32_t* box, CUtensorMapSwizzle swz, CUtensorMapL2promotion promo) {
  cuuint32_t es[5] = {1, 1, 1, 1, 1};
  fn(m, CU_TENSOR_MAP_DATA_TYPE_BFLOAT16, rank, (void*)p, dims, strides, box, es, CU_TENSOR_MAP_INTERLEAVE_NONE, swz, promo,
     CU_TENSOR_MAP_FLOAT_OOB_FILL_NONE);
}

extern "C" void kernel_launch(void* const* d_in, const int* in_sizes, int n_in, void* d_out, int out_size) {
  void* fp = nullptr;
  cudaDriverEntryPointQueryResult qr;
  cudaGetDriverEntryPoint("cuTensorMapEncodeTiled", &fp, cudaEnableDefault, &qr);
  EncodeFn fn = (EncodeFn)fp;
  Params P;
  P.shift_k = (const __nv_bfloat16*)d_in[3]; P.h = (const __nv_bfloat16*)d_in[4]; P.D = (const __nv_bfloat16*)d_in[5];
  P.q = (const __nv_bfloat16*)d_in[0];
  cudaGetSymbolAddress((void**)&P.part, g_part); cudaGetSymbolAddress((void**)&P.kv, g_kv); cudaGetSymbolAddress((void**)&P.o, g_o);
  cudaGetSymbolAddress((void**)&P.thr, c_thr); cudaGetSymbolAddress((void**)&P.img, c_img);
  P.x = (const __nv_bfloat16*)d_in[6]; P.w = (const __nv_bfloat16*)d_in[7]; P.wo = (const __nv_bfloat16*)d_in[8];
  const CUtensorMapSwizzle S128 = CU_TENSOR_MAP_SWIZZLE_128B, S32 = CU_TENSOR_MAP_SWIZZLE_32B;
  const CUtensorMapL2promotion P0 = CU_TENSOR_MAP_L2_PROMOTION_NONE, P128 = CU_TENSOR_MAP_L2_PROMOTION_L2_128B;
  { cuuint64_t d[2] = {1024, 2048}, s[1] = {2048}; cuuint32_t b[2] = {64, 128}; enc(fn, &P.tmX, d_in[6], 2, d, s, b, S128, P128); }
  { cuuint64_t d[2] = {1024, 2048}, s[1] = {2048}; cuuint32_t b[2] = {64, 64}; enc(fn, &P.tmX0, d_in[6], 2, d, s, b, S128, P128); }
  { cuuint64_t d[3] = {1024, 1024, 3}, s[2] = {6144, 2048}; cuuint32_t b[3] = {64, 64, 3}; enc(fn, &P.tmW, d_in[7], 3, d, s, b, S128, P128); }
  { cuuint64_t d[4] = {64, 64, 16, 16}, s[3] = {2048, 131072, 128}; cuuint32_t b[4] = {64, 32, 2, 2}; enc(fn, &P.tmWo, d_in[8], 4, d, s, b, S128, P128); }
  { cuuint64_t d[4] = {64, 64, 16, 16}, s[3] = {2048, 131072, 128}; cuuint32_t b[4] = {64, 32, 2, 1}; enc(fn, &P.tmWo1, d_in[8], 4, d, s, b, S128, P128); }
  { cuuint64_t d[2] = {1024, 2048}, s[1] = {2048}; cuuint32_t b[2] = {16, 72}; enc(fn, &P.tmK, d_in[1], 2, d, s, b, S32, P128); }
  { cuuint64_t d[2] = {1024, 2048}, s[1] = {2048}; cuuint32_t b[2] = {16, 64}; enc(fn, &P.tmV, d_in[2], 2, d, s, b, S32, P128); }
  { cuuint64_t d[5] = {1024, 4, 2, 32, 8}, s[4] = {32768, 16384, 131072, 2048}; cuuint32_t b[5] = {16, 4, 2, 8, 1}; enc(fn, &P.tmQ, d_in[0], 5, d, s, b, S32, P128); }
  { cuuint64_t d[5] = {1024, 4, 2, 32, 8}, s[4] = {65536, 32768, 262144, 4096}; cuuint32_t b[5] = {16, 4, 2, 8, 1}; enc(fn, &P.tmOA, d_out, 5, d, s, b, S32, P0); }
  { cuuint64_t d[2] = {2048, 2048}, s[1] = {4096}; cuuint32_t b[2] = {64, 16}; enc(fn, &P.tmOB, d_out, 2, d, s, b, S128, P0); }
  cudaFuncSetAttribute(fused_kernel, cudaFuncAttributeMaxDynamicSharedMemorySize, SMEM_TOTAL);
  fused_kernel<<<128, 384, SMEM_TOTAL>>>(P);
}
```

```cpp
#include <cuda_runtime.h>
#include <cuda_bf16.h>
#include <cuda_fp16.h>
#include <cuda.h>
#include <stdint.h>

template<int TA, int TB, int SA=1> __device__ __forceinline__ void wgmma_ss_n192(float (&d)[96], uint64_t da, uint64_t db, int scale_d) {
  asm volatile("{\n.reg .pred p;\nsetp.ne.b32 p, %98, 0;\n"
    "wgmma.mma_async.sync.aligned.m64n192k16.f32.bf16.bf16 {%0, %1, %2, %3, %4, %5, %6, %7, %8, %9, %10, %11, %12, %13, %14, %15, %16, %17, %18, %19, %20, %21, %22, %23, %24, %25, %26, %27, %28, %29, %30, %31, %32, %33, %34, %35, %36, %37, %38, %39, %40, %41, %42, %43, %44, %45, %46, %47, %48, %49, %50, %51, %52, %53, %54, %55, %56, %57, %58, %59, %60, %61, %62, %63, %64, %65, %66, %67, %68, %69, %70, %71, %72, %73, %74, %75, %76, %77, %78, %79, %80, %81, %82, %83, %84, %85, %86, %87, %88, %89, %90, %91, %92, %93, %94, %95}, %96, %97, p, %101, 1, %99, %100;\n}\n"
    : "+f"(d[0]), "+f"(d[1]), "+f"(d[2]), "+f"(d[3]), "+f"(d[4]), "+f"(d[5]), "+f"(d[6]), "+f"(d[7]), "+f"(d[8]), "+f"(d[9]), "+f"(d[10]), "+f"(d[11]), "+f"(d[12]), "+f"(d[13]), "+f"(d[14]), "+f"(d[15]), "+f"(d[16]), "+f"(d[17]), "+f"(d[18]), "+f"(d[19]), "+f"(d[20]), "+f"(d[21]), "+f"(d[22]), "+f"(d[23]), "+f"(d[24]), "+f"(d[25]), "+f"(d[26]), "+f"(d[27]), "+f"(d[28]), "+f"(d[29]), "+f"(d[30]), "+f"(d[31]), "+f"(d[32]), "+f"(d[33]), "+f"(d[34]), "+f"(d[35]), "+f"(d[36]), "+f"(d[37]), "+f"(d[38]), "+f"(d[39]), "+f"(d[40]), "+f"(d[41]), "+f"(d[42]), "+f"(d[43]), "+f"(d[44]), "+f"(d[45]), "+f"(d[46]), "+f"(d[47]), "+f"(d[48]), "+f"(d[49]), "+f"(d[50]), "+f"(d[51]), "+f"(d[52]), "+f"(d[53]), "+f"(d[54]), "+f"(d[55]), "+f"(d[56]), "+f"(d[57]), "+f"(d[58]), "+f"(d[59]), "+f"(d[60]), "+f"(d[61]), "+f"(d[62]), "+f"(d[63]), "+f"(d[64]), "+f"(d[65]), "+f"(d[66]), "+f"(d[67]), "+f"(d[68]), "+f"(d[69]), "+f"(d[70]), "+f"(d[71]), "+f"(d[72]), "+f"(d[73]), "+f"(d[74]), "+f"(d[75]), "+f"(d[76]), "+f"(d[77]), "+f"(d[78]), "+f"(d[79]), "+f"(d[80]), "+f"(d[81]), "+f"(d[82]), "+f"(d[83]), "+f"(d[84]), "+f"(d[85]), "+f"(d[86]), "+f"(d[87]), "+f"(d[88]), "+f"(d[89]), "+f"(d[90]), "+f"(d[91]), "+f"(d[92]), "+f"(d[93]), "+f"(d[94]), "+f"(d[95])
    : "l"(da), "l"(db), "r"(scale_d), "n"(TA), "n"(TB), "n"(SA));
}
template<int TA, int TB, int SA=1> __device__ __forceinline__ void wgmma_ss_n128(float (&d)[64], uint64_t da, uint64_t db, int scale_d) {
  asm volatile("{\n.reg .pred p;\nsetp.ne.b32 p, %66, 0;\n"
    "wgmma.mma_async.sync.aligned.m64n128k16.f32.bf16.bf16 {%0, %1, %2, %3, %4, %5, %6, %7, %8, %9, %10, %11, %12, %13, %14, %15, %16, %17, %18, %19, %20, %21, %22, %23, %24, %25, %26, %27, %28, %29, %30, %31, %32, %33, %34, %35, %36, %37, %38, %39, %40, %41, %42, %43, %44, %45, %46, %47, %48, %49, %50, %51, %52, %53, %54, %55, %56, %57, %58, %59, %60, %61, %62, %63}, %64, %65, p, %69, 1, %67, %68;\n}\n"
    : "+f"(d[0]), "+f"(d[1]), "+f"(d[2]), "+f"(d[3]), "+f"(d[4]), "+f"(d[5]), "+f"(d[6]), "+f"(d[7]), "+f"(d[8]), "+f"(d[9]), "+f"(d[10]), "+f"(d[11]), "+f"(d[12]), "+f"(d[13]), "+f"(d[14]), "+f"(d[15]), "+f"(d[16]), "+f"(d[17]), "+f"(d[18]), "+f"(d[19]), "+f"(d[20]), "+f"(d[21]), "+f"(d[22]), "+f"(d[23]), "+f"(d[24]), "+f"(d[25]), "+f"(d[26]), "+f"(d[27]), "+f"(d[28]), "+f"(d[29]), "+f"(d[30]), "+f"(d[31]), "+f"(d[32]), "+f"(d[33]), "+f"(d[34]), "+f"(d[35]), "+f"(d[36]), "+f"(d[37]), "+f"(d[38]), "+f"(d[39]), "+f"(d[40]), "+f"(d[41]), "+f"(d[42]), "+f"(d[43]), "+f"(d[44]), "+f"(d[45]), "+f"(d[46]), "+f"(d[47]), "+f"(d[48]), "+f"(d[49]), "+f"(d[50]), "+f"(d[51]), "+f"(d[52]), "+f"(d[53]), "+f"(d[54]), "+f"(d[55]), "+f"(d[56]), "+f"(d[57]), "+f"(d[58]), "+f"(d[59]), "+f"(d[60]), "+f"(d[61]), "+f"(d[62]), "+f"(d[63])
    : "l"(da), "l"(db), "r"(scale_d), "n"(TA), "n"(TB), "n"(SA));
}
template<int TA, int TB, int SA=1> __device__ __forceinline__ void wgmma_ss_n72(float (&d)[36], uint64_t da, uint64_t db, int scale_d) {
  asm volatile("{\n.reg .pred p;\nsetp.ne.b32 p, %38, 0;\n"
    "wgmma.mma_async.sync.aligned.m64n72k16.f32.bf16.bf16 {%0, %1, %2, %3, %4, %5, %6, %7, %8, %9, %10, %11, %12, %13, %14, %15, %16, %17, %18, %19, %20, %21, %22, %23, %24, %25, %26, %27, %28, %29, %30, %31, %32, %33, %34, %35}, %36, %37, p, %41, 1, %39, %40;\n}\n"
    : "+f"(d[0]), "+f"(d[1]), "+f"(d[2]), "+f"(d[3]), "+f"(d[4]), "+f"(d[5]), "+f"(d[6]), "+f"(d[7]), "+f"(d[8]), "+f"(d[9]), "+f"(d[10]), "+f"(d[11]), "+f"(d[12]), "+f"(d[13]), "+f"(d[14]), "+f"(d[15]), "+f"(d[16]), "+f"(d[17]), "+f"(d[18]), "+f"(d[19]), "+f"(d[20]), "+f"(d[21]), "+f"(d[22]), "+f"(d[23]), "+f"(d[24]), "+f"(d[25]), "+f"(d[26]), "+f"(d[27]), "+f"(d[28]), "+f"(d[29]), "+f"(d[30]), "+f"(d[31]), "+f"(d[32]), "+f"(d[33]), "+f"(d[34]), "+f"(d[35])
    : "l"(da), "l"(db), "r"(scale_d), "n"(TA), "n"(TB), "n"(SA));
}
template<int TB, int SA=1> __device__ __forceinline__ void wgmma_rs_n40(float (&d)[20], uint32_t a0, uint32_t a1, uint32_t a2, uint32_t a3, uint64_t db, int scale_d) {
  asm volatile("{\n.reg .pred p;\nsetp.ne.b32 p, %25, 0;\n"
    "wgmma.mma_async.sync.aligned.m64n40k16.f32.bf16.bf16 {%0, %1, %2, %3, %4, %5, %6, %7, %8, %9, %10, %11, %12, %13, %14, %15, %16, %17, %18, %19}, {%20, %21, %22, %23}, %24, p, %27, 1, %26;\n}\n"
    : "+f"(d[0]), "+f"(d[1]), "+f"(d[2]), "+f"(d[3]), "+f"(d[4]), "+f"(d[5]), "+f"(d[6]), "+f"(d[7]), "+f"(d[8]), "+f"(d[9]), "+f"(d[10]), "+f"(d[11]), "+f"(d[12]), "+f"(d[13]), "+f"(d[14]), "+f"(d[15]), "+f"(d[16]), "+f"(d[17]), "+f"(d[18]), "+f"(d[19])
    : "r"(a0), "r"(a1), "r"(a2), "r"(a3), "l"(db), "r"(scale_d), "n"(TB), "n"(SA));
}
template<int TB> __device__ __forceinline__ void wgmma_hrs_n64(uint32_t (&d)[16], uint32_t a0, uint32_t a1, uint32_t a2, uint32_t a3, uint64_t db, int scale_d) {
  asm volatile("{\n.reg .pred p;\nsetp.ne.b32 p, %21, 0;\n"
    "wgmma.mma_async.sync.aligned.m64n64k16.f16.f16.f16 {%0, %1, %2, %3, %4, %5, %6, %7, %8, %9, %10, %11, %12, %13, %14, %15}, {%16, %17, %18, %19}, %20, p, 1, 1, %22;\n}\n"
    : "+r"(d[0]), "+r"(d[1]), "+r"(d[2]), "+r"(d[3]), "+r"(d[4]), "+r"(d[5]), "+r"(d[6]), "+r"(d[7]), "+r"(d[8]), "+r"(d[9]), "+r"(d[10]), "+r"(d[11]), "+r"(d[12]), "+r"(d[13]), "+r"(d[14]), "+r"(d[15])
    : "r"(a0), "r"(a1), "r"(a2), "r"(a3), "l"(db), "r"(scale_d), "n"(TB));
}
template<int TB> __device__ __forceinline__ void wgmma_hrs_n32(uint32_t (&d)[8], uint32_t a0, uint32_t a1, uint32_t a2, uint32_t a3, uint64_t db, int scale_d) {
  asm volatile("{\n.reg .pred p;\nsetp.ne.b32 p, %13, 0;\n"
    "wgmma.mma_async.sync.aligned.m64n32k16.f16.f16.f16 {%0, %1, %2, %3, %4, %5, %6, %7}, {%8, %9, %10, %11}, %12, p, 1, 1, %14;\n}\n"
    : "+r"(d[0]), "+r"(d[1]), "+r"(d[2]), "+r"(d[3]), "+r"(d[4]), "+r"(d[5]), "+r"(d[6]), "+r"(d[7])
    : "r"(a0), "r"(a1), "r"(a2), "r"(a3), "l"(db), "r"(scale_d), "n"(TB));
}

__device__ __align__(128) const uint32_t c_thr[1536] = {
  0x33fb33ff,0xa49c9de4,0x33273352,0xaf2cae76,0x33e233f1,0xa96ca7bd,0x32c432f7,0xb045afdd,0x33b733cf,0xac3eaaf7,0x3250328c,0xb0eab099,
  0x3378339a,0xadbcacff,0x31cd3211,0xb182b137,0x33d033fb,0xaadea46a,0x299e2d17,0xb3e0b396,0x32fb337a,0xafd2adb1,0xa78b1f76,0xb3f2b3ff,
  0x318b3254,0xb1c5b0e5,0xae6bac32,0xb354b3b8,0x2f4230a3,0xb321b285,0xb133b040,0xb215b2c7,0x337c33f2,0xada5a759,0xb179afc8,0xb1d6b2fe,
  0x31463293,0xb204b08e,0xb394b2ba,0xad23b055,0x2b402f4e,0xb3cbb31e,0xb3e4b3f9,0x293ba533,0xac269c52,0xb3bab400,0xb258b357,0x30e02e5f,
  0x330133e5,0xafbda922,0xb3f3b3c9,0x2727ab59,0x2deb314a,0xb36fb200,0xb194b32f,0x31bc2f0a,0xacdb2084,0xb39fb3ff,0xa565aea4,0x33f93347,
  0xb2b6b0db,0xb05ab25c,0x30892c1a,0x329733bc,0x326033d4,0xb0d6aa94,0xb00ab29b,0x32e83084,0x20e82f64,0xb3feb318,0x2d8da597,0x338133f8,
  0xb1fcae48,0xb14fb35c,0x339031b8,0x2d3a3199,0xb3e6b3ae,0x2909ac7b,0x32d133f4,0xb030a6f5,0x319d33bf,0xb1b3ac02,0x2e3ca874,0x335e33ec,
  0xacc32b89,0xb3a3b3c6,0x33f83276,0x25c930b7,0xb3dcb1f8,0xaa01b154,0x30653335,0xb2b0aef4,0xb107b383,0x32392d81,0xafa6214d,0xb307b3fe,
  0x30bc33a5,0xb273acb7,0x33c5311b,0x2ba23229,0xb0cc94b6,0xb267b400,0x30153360,0xb2e1ae31,0xb385b3ab,0x2d76ac93,0xb166a691,0xb1e7b3f5,
  0x22deb06a,0x33fd32ac,0xb337b3da,0x2ee8aa19,0x2f853387,0xb310ad6a,0x322d33fe,0xb1162216,0xb2a9abd3,0xb06fb3c2,0xb07428a6,0xb2a5b3ea,
  0xb111b3e9,0x323128be,0xb30db3c3,0x2f90abba,0x31aa227a,0x31a633fd,0x2e25ad5e,0x33633389,0x2d6a3365,0xb387ae1a,0xa21631aa,0xb3feb1a6,
  0xb3c2af85,0xabd3b310,0xb3eab22d,0x28a6b116,0xa8beb2a9,0x33e9306f,0x2bbab074,0x33c332a5,0x33fd3111,0x227a3231,0x3389330d,0xad5e2f90,
  0x2a63333f,0xb3d7aec6,0xb2a2a1b1,0xb07ab3fe,0xb3f7b158,0x25fbb1f4,0xacb7b38b,0x33a52d52,0x2e0eb025,0x336832d8,0x340030bc,0x14b63273,
  0x323533c0,0xb10c2beb,0xac9330cc,0xb3abb267,0x23433316,0xb3fdaf6f,0xb38eb225,0x2d46b11f,0xb342b29e,0x2ebbb07f,0x31e3aa7c,0x316b33d6,
  0x3264a6c3,0x30d133f5,0x2c0233ac,0xb3bfac87,0x28f0336a,0xb3e7ae02,0xb3c6b19d,0x2b89b1b3,0xa59732e8,0xb3f8b00a,0xaccfb3ed,0x33a1285b,
  0xb1b8b381,0x3199ad8d,0x336c31df,0xadf73170,0x33f42d3a,0x26f53390,0xb30423a7,0xafb2b3fc,0xb05f3030,0xb2b3b2d1,0x29e8b27a,0x33dd30b2,
  0xab5932b6,0xb3c9b05a,0x30adb089,0x327e3297,0xaf0ab3f3,0x332fa727,0x240633b0,0xb3fcac6f,0x33473194,0xaea431bc,0xb174b359,0x31daae54,
  0xb3bca565,0xac1ab3f9,0x33ee2f59,0xa842331b,0xaddf3281,0xb371b0a8,0x34002b40,0x1c5233cb,0xa759b3ef,0x33f22829,0xb2fe2c26,0xafc8b3ba,
  0x308e337c,0xb2932da5,0x3055b179,0x32ba31d6,0xb31eb146,0x2f4eb204,0xa5333394,0xb3f9ad23,0xaff33249,0xb2f1b0f3,0x30e532fb,0xb2542fd2,
  0x2b28b373,0x33cc2dd4,0xb285b18b,0x30a3b1c5,0x246a33fa,0xb3fba500,0x33962f42,0xad173321,0xadb1b3d0,0x337aaade,0xb3ffa99e,0x1f76b3e0,
  0xb0ee320d,0xb24db13c,0xac4b3398,0xb3b5ad0b,0x304ab289,0x32c1309e,0x2985b3ce,0x33e12b0f,0xaf3732f4,0xb324afe8,0xa4ce33f0,0xb3faa7ef,
  0x2dc8b34f,0x33762e82,0x9de4b3ff,0x33ff1ead,0xb1c931cd,0xb186b182,0xb3762e82,0xadc8b34f,0x324db13c,0x30ee320d,0x33b5ad0b,0x2c4b3398,
  0xb2c1309e,0xb04ab289,0xb3e12b0f,0xa985b3ce,0x3324afe8,0x2f3732f4,0x33faa7ef,0x24ce33f0,0xb285318b,0xb0a3b1c5,0xb2c7ae6b,0x3040b354,
  0x3396af42,0x2d173321,0x31413133,0xb2093215,0xb3ff299e,0x9f76b3e0,0xae8db2bd,0x334cb050,0x33b8278b,0xac3233f2,0x281033b3,0xb3ef2c57,
  0xb31e3146,0xaf4eb204,0xa533b394,0x33f9ad23,0x3400ab40,0x9c5233cb,0xae5f33e4,0xb357a93b,0xb2feac26,0x2fc8b3ba,0x3245b258,0x30f830e0,
  0x30553179,0xb2ba31d6,0xb3df2e99,0xa9b6b34a,0xb39230fd,0xad2fb241,0x3200b301,0x314a2fbd,0x337f1b11,0xad993400,0xb3ff2deb,0xa084b36f,
  0xb005b129,0x32ebb21d,0x325c2cdb,0xb0db339f,0xa92233de,0xb3e529cf,0xab59b2b6,0x33c9b05a,0xb3dd30b2,0xa9e8b27a,0x33d4ab71,0xaa9433c8,
  0x32212c0e,0xb12433bd,0xaf64b0d6,0x3318b260,0x197fb345,0x3400aeaf,0xae4833fe,0xb35c20e8,0xb23d3332,0xb102aeff,0x33aeb14f,0x2c7b31fc,
  0xb3fe3065,0xa14db2b0,0x2ebb307f,0xb342329e,0x300f2fa6,0xb2e53307,0x30d1b3f5,0x326426c3,0x302ab400,0x32d517db,0xb3e72e02,0x28f0b36a,
  0xb3fd2f6f,0x2343b316,0x2d46311f,0xb38e3225,0xb3f53015,0x2691b2e1,0xaf9b33eb,0xb30a288d,0x2a193166,0xb3da31e7,0x33d7aec6,0xaa63333f,
  0x3313b337,0x2f7a2ee8,0xa5fbb1f4,0x33f7b158,0xb1a1a8d7,0x31afb3e8,0xb36832d8,0xae0eb025,0xb3c22f85,0x2bd3b310,0xb3ea322d,0xa8a6b116,
  0xa8be32a9,0xb3e9306f,0x2bba3074,0xb3c332a5,0x33fdb111,0xa27a3231,0x3389b30d,0x2d5e2f90,0xa216b1aa,0x33feb1a6,0xaed2ae25,0x333db363,
  0xb3652edd,0x2e1ab33a,0xb1aa227a,0x31a6b3fd,0xaf853387,0xb3102d6a,0xb22d33fe,0xb116a216,0x32a9abd3,0xb06f33c2,0x307428a6,0xb2a533ea,
  0x3111b3e9,0x3231a8be,0x330db3c3,0x2f902bba,0xb2e12e31,0x3015b360,0x288db1a1,0x33ebb1af,0xb1e733f5,0xb1662691,0xb33f2f9b,0x2ec6b30a,
  0x2ee82a19,0xb33733da,0xb15833d7,0xb1f42a63,0x33e8b313,0x28d72f7a,0x302525fb,0xb2d833f7,0xb2392d81,0x3107b383,0x3307b3fe,0x2fa6214d,
  0xb35e33ec,0xae3ca874,0x97dbb00f,0x3400b2e5,0xa5c930b7,0xb3f83276,0xb316302a,0x2f6fb2d5,0x32b0aef4,0xb0653335,0xb29e33fd,0xb07f2343,
  0xb1702ccf,0x31dfb3a1,0x3345b124,0xaeaf3221,0xb3fc336c,0xa3a7adf7,0x3332b400,0x2eff997f,0xb0b23304,0xb27a2fb2,0x2b71b102,0x33c8b23d,
  0x2c0e29e8,0xb3bd33dd,0xb0d62a94,0x3260b3d4,0xb0892c1a,0x3297b3bc,0x2aad2842,0xb3d333ee,0xb3b0327e,0x2c6fb0ad,0x3241b035,0xb0fd32ce,
  0xb35933fc,0xae542406,0x3400b392,0x1b112d2f,0xaf5931da,0xb31b3174,0x321db37f,0x3129ad99,0xaf152ac6,0x332cb3d2,0xb1463293,0xb204308e,
  0xb281312e,0x30a8b219,0xab402f4e,0xb3cb331e,0xb3ef3371,0x2829addf,0x2c269c52,0xb3ba3400,0xb37c33f2,0xada52759,0x3179afc8,0xb1d632fe,
  0xacf32953,0x339cb3e3,0xb3fa33cc,0x2500ab28,0xb0942f21,0x3290b32a,0xb3d033fb,0xaade246a,0xb249317d,0x30f3b1d2,0xb2fb337a,0xafd22db1,
  0xb37332f1,0x2dd4aff3,0xb18b3254,0xb1c530e5,0xa96c27bd,0x33e2b3f1,0xb0452fdd,0x32c4b2f7,0xac3e2af7,0x33b7b3cf,0xb0ea3099,0x3250b28c,
  0xadbc2cff,0x3378b39a,0xb1823137,0x31cdb211,0xaf2c2e76,0x3327b352,0xb20d31c9,0x313cb186,0x313c3186,0xb20db1c9,0x2d0b2dc8,0xb398b376,
  0x309e30ee,0xb289b24d,0x2b0f2c4b,0xb3ceb3b5,0x2fe8304a,0xb2f4b2c1,0x27ef2985,0xb3f0b3e1,0x2e822f37,0xb34fb324,0x1ead24ce,0xb3ffb3fa,
  0xb2bdb209,0xb050b141,0xb290b32a,0x30942f21,0xb3b3b34c,0xac57ae8d,0xb0f3b1d2,0x3249317d,0xb400b3ef,0x1d1ba810,0xadd4aff3,0x337332f1,
  0xb39cb3e3,0x2cf32953,0xa500ab28,0x33fa33cc,0xae99b0f8,0x334a3245,0x33ff33b2,0x201f2c63,0x2438a9b6,0x33fc33df,0x332c33d2,0xaf15aac6,
  0x303a2ce7,0x32cb339e,0x30a83219,0xb281b12e,0x32ee31c0,0x2ffe3190,0x28292ddf,0xb3efb371,0x33b0327e,0x2c6f30ad,0xb241b035,0xb0fdb2ce,
  0x335933fc,0xae54a406,0xb400b392,0x1b11ad2f,0x2f5931da,0xb31bb174,0xb21db37f,0x31292d99,0xaaad2842,0xb3d3b3ee,0xa9cfb005,0x33de32eb,
  0x285b305f,0xb3edb2b3,0x2c0ea9e8,0x33bd33dd,0xb170accf,0xb1dfb3a1,0x33453124,0x2eaf3221,0xb3fcb36c,0x23a7adf7,0x33323400,0xaeff997f,
  0xb0b2b304,0x327a2fb2,0x2b713102,0xb3c8b23d,0xb400b2e5,0x17dbb00f,0x2e023264,0xb36ab0d1,0xaf6fb2d5,0x3316302a,0xb11fa8f0,0xb225b3e7,
  0x307f2343,0x329e33fd,0xb3d6b38e,0x2a7cad46,0x33f53342,0xa6c32ebb,0xac87b1e3,0x33ac316b,0x28d7af7a,0x33e83313,0xb2d8b3f7,0x3025a5fb,
  0x33eb31af,0x288d31a1,0x2bebae0e,0x33c03368,0x2ec6330a,0xb33faf9b,0x33fe3235,0x21b1310c,0xb1f4aa63,0xb158b3d7,0x2d5232a2,0xb38bb07a,
  0x33a7333d,0xacab2ed2,0x33f63162,0x262d31eb,0xaa4b301a,0xb3d8b2de,0x2a32326b,0xb3d9b0c7,0xb3f6b26f,0x265fb0c1,0xb3a9b020,0xac9fb2db,
  0x0e48b15d,0x340031f0,0xae1ab33a,0x33652edd,0xaed22e25,0xb33db363,0xb1eb0e48,0xb162b400,0xb2deb3a7,0x301aacab,0xb0c7b3f6,0x326b262d,
  0x30c1aa4b,0x326f33d8,0x32db2a32,0x302033d9,0x31f033f6,0xb15d265f,0x2edd33a9,0xb33aac9f,0xb2acb385,0x306aad76,0x2a19b166,0x33da31e7,
  0x3229a2de,0x311b33fd,0x33133337,0xaf7a2ee8,0x2e3133c5,0xb360aba2,0xb1a128d7,0xb1afb3e8,0xb3f5b015,0xa691b2e1,0xaf9bb3eb,0x330a288d,
  0x3154acc3,0x31f833a3,0x2ef433f8,0xb335a5c9,0x2d8133dc,0xb383aa01,0xb3feb065,0x214db2b0,0xb3ecb107,0x2874b239,0x300fafa6,0x32e53307,
  0x30b7ae3c,0x3276335e,0x302a3400,0xb2d517db,0x312433bd,0xb2212c0e,0xb318b260,0x2f64b0d6,0xb400aeaf,0x997fb345,0x335c20e8,0x2e4833fe,
  0x3102aeff,0x323d3332,0xac7b31fc,0xb3aeb14f,0x2a9433c8,0xb3d4ab71,0xb084b3e6,0x329ba909,0xb2ce2aad,0xb035b3d3,0x33e529cf,0x292233de,
  0x2d2fb241,0x339230fd,0xb14a2fbd,0xb200b301,0x2d993400,0xb37f1b11,0x2084b36f,0x33ff2deb,0xb2ebb21d,0x3005b129,0x30db339f,0xb25c2cdb,
  0xae5fb3e4,0x3357a93b,0xb190303a,0xb1c0b2cb,0x32453258,0xb0f830e0,0x2c63b2ee,0x33b22ffe,0xb3dfae99,0x29b6b34a,0x2ac633ff,0xb3d2a01f,
  0x339ea438,0x2ce733fc,0xb12eb32c,0x3219af15,0x33b8a78b,0x2c3233f2,0x2810b3b3,0x33ef2c57,0xb2c72e6b,0xb040b354,0x29533400,0xb3e31d1b,
  0x3141b133,0x32093215,0xaf21b39c,0x332aacf3,0xae8d32bd,0xb34cb050,0x317d3290,0xb1d23094,0x27bd33fb,0xb3f1249c,0x2fdd3327,0xb2f72f2c,
  0xaaf7b3e2,0x33cfa96c,0xb099b2c4,0x328cb045,0x2cff33b7,0xb39a2c3e,0x31373250,0xb21130ea,0xae76b378,0x3352adbc,0xb1c9b1cd,0x3186b182,
  0xb3ff1ead,0x1de4b3ff,0xb352adbc,0x2e76b378,0x33f1249c,0xa7bd33fb,0x32f72f2c,0xafdd3327,0xb3cfa96c,0x2af7b3e2,0xb28cb045,0x3099b2c4,
  0x339a2c3e,0xacff33b7,0x321130ea,0xb1373250,0x2953b400,0x33e31d1b,0x33ccadd4,0x2b283373,0xaf21339c,0xb32aacf3,0xb3fb2500,0x246ab3fa,
  0x317db290,0x31d23094,0x337a2ade,0xadb133d0,0xb2f130f3,0xaff3b249,0xb254afd2,0x30e5b2fb,0x339e2438,0xace733fc,0xb12e332c,0xb219af15,
  0xb190b03a,0x31c0b2cb,0x3371b0a8,0x2ddf3281,0x2c6332ee,0xb3b22ffe,0xb3f22829,0x2759b3ef,0x2ac6b3ff,0x33d2a01f,0x32932da5,0xb08e337c,
  0xaf0a33f3,0xb32fa727,0x2406b3b0,0x33fcac6f,0x3347b194,0x2ea431bc,0xb1743359,0xb1daae54,0xb3bc2565,0x2c1ab3f9,0x33eeaf59,0x2842331b,
  0x30ad3089,0xb27e3297,0xb2ceaaad,0x3035b3d3,0xb29ba909,0x3084b3e6,0x305f3030,0xb2b332d1,0x259732e8,0xb3f8300a,0x2ccfb3ed,0x33a1a85b,
  0x31b8b381,0x31992d8d,0xb36c31df,0xadf7b170,0xb3f42d3a,0x26f5b390,0x330423a7,0xafb233fc,0x316bb3d6,0x31e32a7c,0xb3832a01,0x2d81b3dc,
  0xb3bf2c87,0x2c02b3ac,0x28743239,0xb3ec3107,0x2b8931b3,0xb3c6319d,0x3276b35e,0x30b72e3c,0x31f8b3a3,0x31542cc3,0xb33525c9,0x2ef4b3f8,
  0x310c2beb,0xb23533c0,0x33abb267,0x2c9330cc,0x307ab3fe,0x32a2a1b1,0xb06aad76,0x32acb385,0xb3a52d52,0x2cb7b38b,0xb11b33fd,0xb229a2de,
  0x94b63273,0xb40030bc,0x3360aba2,0xae3133c5,0xb2de33a7,0xb01aacab,0xb0c733f6,0xb26b262d,0x30c12a4b,0xb26f33d8,0x32dbaa32,0xb02033d9,
  0x31f0b3f6,0x315d265f,0x2eddb3a9,0x333aac9f,0xb1eb8e48,0x3162b400,0xb3872e1a,0x2d6ab365,0xae25ad5e,0x3363b389,0x8e48b15d,0x3400b1f0,
  0xb3a7333d,0xacabaed2,0xb3f63162,0x262db1eb,0x2a4b301a,0xb3d832de,0xaa32326b,0xb3d930c7,0x33f6b26f,0x265f30c1,0x33a9b020,0xac9f32db,
  0x33c0b368,0x2beb2e0e,0x30cc94b6,0xb2673400,0x21b1b10c,0x33feb235,0x3385b3ab,0x2d762c93,0xb38b307a,0x2d52b2a2,0xa2deb06a,0x33fdb2ac,
  0xb0bc33a5,0xb2732cb7,0xb3c5311b,0x2ba2b229,0x26c32ebb,0xb3f53342,0xb3ac316b,0x2c87b1e3,0x336ab0d1,0xae023264,0xb19d33bf,0xb1b32c02,
  0x3225b3e7,0x311fa8f0,0x2cc32b89,0xb3a333c6,0xaa7cad46,0x33d6b38e,0x33dcb1f8,0xaa013154,0xb3fe3318,0x20e8af64,0x3381b3f8,0x2d8d2597,
  0xb14f335c,0xb1fc2e48,0x2d3ab199,0x3390b1b8,0x29092c7b,0xb3e633ae,0xb03026f5,0x32d1b3f4,0x32e8b084,0xb00a329b,0xb3ed32b3,0x285bb05f,
  0x29cfb005,0x33deb2eb,0xb05a325c,0xb2b630db,0xafbd2922,0x3301b3e5,0x27272b59,0xb3f333c9,0xb36f3200,0x2debb14a,0x31bcaf0a,0xb194332f,
  0xb39f33ff,0xacdba084,0x33f9b347,0xa5652ea4,0x3394b2ba,0xad233055,0xa438a9b6,0x33fcb3df,0x33e4b3f9,0x293b2533,0xb03a2ce7,0x32cbb39e,
  0x3258b357,0x30e0ae5f,0xb2ee31c0,0x2ffeb190,0x2e99b0f8,0x334ab245,0xb3ff33b2,0x201fac63,0xaf4230a3,0xb3213285,0x3133b040,0xb21532c7,
  0xa99e2d17,0xb3e03396,0x32bdb209,0xb0503141,0x278b1f76,0xb3f233ff,0x33b3b34c,0xac572e8d,0x2e6bac32,0xb35433b8,0x3400b3ef,0x1d1b2810,
  0xb289324d,0x309eb0ee,0xb3ce33b5,0x2b0fac4b,0xb2f432c1,0x2fe8b04a,0xb3f033e1,0x27efa985,0xb34f3324,0x2e82af37,0xb3ff33fa,0x1eada4ce,
  0xb3983376,0x2d0badc8,0xb3fb33ff,0xa49c1de4,0x351c35f6,0xac93a617,0xb8a3b93c,0x308d2a16,0x32f43448,0xb160afa5,0xb6a4b7fe,0x353a3389,
  0x2fa53160,0xb448b2f4,0xb389b53a,0x37fe36a4,0x26172c93,0xb5f6b51c,0xaa16b08d,0x393c38a3,0x34c3358c,0xac47a5b2,0xb85fb8f3,0x304229b1,
  0x327e33fd,0xb106af26,0xb63cb785,0x34e7330f,0x2f263106,0xb3fdb27e,0xb30fb4e7,0x3785363c,0x25b22c47,0xb58cb4c3,0xa9b1b042,0x38f3385f,
  0x346a3523,0xabf6a54d,0xb81ab8a8,0x2fef294d,0x3209336b,0xb0acaea7,0xb5d4b70a,0x34933294,0x2ea730ac,0xb36bb209,0xb294b493,0x370a35d4,
  0x254d2bf6,0xb523b46a,0xa94dafef,0x38a8381a,0x341334bc,0xab5fa4e9,0xb7a6b85a,0x2f5928e8,0x319432da,0xb052ae28,0xb56ab68d,0x343e3219,
  0x2e283052,0xb2dab194,0xb219b43e,0x368d356a,0x24e92b5f,0xb4bcb413,0xa8e8af59,0x385a37a6,0x33783456,0xaac8a484,0xb715b80a,0x2ec32884,
  0x3120324a,0xaff2ada9,0xb4ffb60e,0x33d3319e,0x2da92ff2,0xb24ab120,0xb19eb3d3,0x360e34ff,0x24842ac8,0xb456b378,0xa884aec3,0x380a3715,
  0x32cd33e3,0xaa31a420,0xb682b76f,0x2e2d281f,0x30ac31bb,0xaf3fad2a,0xb493b58d,0x33283122,0x2d2a2f3f,0xb1bbb0ac,0xb122b328,0x358d3493,
  0x24202a31,0xb3e3b2cd,0xa81fae2d,0x376f3682,0x3223331c,0xa999a376,0xb5ebb6c6,0x2d972776,0x3039312d,0xae8dacac,0xb426b50b,0x327c30a6,
  0x2cac2e8d,0xb12db039,0xb0a6b27c,0x350b3426,0x23762999,0xb31cb223,0xa776ad97,0x36c635eb,0x317a3257,0xa902a2ad,0xb552b61a,0x2d0026ad,
  0x2f8c309f,0xaddcac2e,0xb371b487,0x31cf3029,0x2c2e2ddc,0xb09faf8c,0xb029b1cf,0x34873371,0x22ad2902,0xb257b17a,0xa6adad00,0x361a3552,
  0x30d23194,0xa86ba1e4,0xb4b7b56a,0x2c6a25e4,0x2ea73012,0xad2aab5f,0xb294b402,0x31222f59,0x2b5f2d2a,0xb012aea7,0xaf59b122,0x34023294,
  0x21e4286b,0xb194b0d2,0xa5e4ac6a,0x356a34b7,0x302c30d2,0xa7a9a11b,0xb41ab4b7,0x2ba7251b,0x2dc22f0c,0xac79aa63,0xb1b6b2f7,0x30742e5f,
  0x2a632c79,0xaf0cadc2,0xae5fb074,0x32f731b6,0x211b27a9,0xb0d2b02c,0xa51baba7,0x34b7341a,0x2f0c3012,0xa67ba052,0xb2f7b402,0x2a7a2452,
  0x2cde2df5,0xab91a967,0xb0d7b1e8,0x2f8b2d65,0x29672b91,0xadf5acde,0xad65af8b,0x31e830d7,0x2052267b,0xb012af0c,0xa452aa7a,0x340232f7,
  0x2dc22ea7,0xa54d9f12,0xb1b6b294,0x294d2311,0x2bf62cde,0xaa31a86b,0xafefb0d7,0x2e2d2c6a,0x286b2a31,0xacdeabf6,0xac6aae2d,0x30d72fef,
  0x1f12254d,0xaea7adc2,0xa311a94d,0x329431b6,0x2c792d2a,0xa4209d7f,0xb074b122,0x281f217f,0x2a312b91,0xa8d0a6e0,0xae2daf8b,0x2cce2ade,
  0x26e028d0,0xab91aa31,0xaadeacce,0x2f8b2e2d,0x1d7f2420,0xad2aac79,0xa17fa81f,0x31223074,0x2a632b5f,0xa1e49bdb,0xae5faf59,0x25e41fdb,
  0x286b2967,0xa6e0a4e9,0xac6aad65,0x2ade28e8,0x24e926e0,0xa967a86b,0xa8e8aade,0x2d652c6a,0x1bdb21e4,0xab5faa63,0x9fdba5e4,0x2f592e5f,
  0x27a9286b,0x9f1298b6,0xaba7ac6a,0x23111cb6,0x254d267b,0xa420a1e4,0xa94daa7a,0x281f25e4,0x21e42420,0xa67ba54d,0xa5e4a81f,0x2a7a294d,
  0x18b61f12,0xa86ba7a9,0x9cb6a311,0x2c6a2ba7,0x211b21e4,0x98b69248,0xa51ba5e4,0x1cb61648,0x1f122052,0x9d7f9bdb,0xa311a452,0x217f1fdb,
  0x1bdb1d7f,0xa0529f12,0x9fdba17f,0x24522311,0x124818b6,0xa1e4a11b,0x96489cb6,0x25e4251b,0xa11ba1e4,0x18b61248,0x251b25e4,0x9cb69648,
  0x9f12a052,0x1d7f1bdb,0x23112452,0xa17f9fdb,0x9bdb9d7f,0x20521f12,0x1fdb217f,0xa452a311,0x924898b6,0x21e4211b,0x16481cb6,0xa5e4a51b,
  0xa7a9a86b,0x1f1218b6,0x2ba72c6a,0xa3119cb6,0xa54da67b,0x242021e4,0x294d2a7a,0xa81fa5e4,0xa1e4a420,0x267b254d,0x25e4281f,0xaa7aa94d,
  0x98b69f12,0x286b27a9,0x1cb62311,0xac6aaba7,0xaa63ab5f,0x21e41bdb,0x2e5f2f59,0xa5e49fdb,0xa86ba967,0x26e024e9,0x2c6a2d65,0xaadea8e8,
  0xa4e9a6e0,0x2967286b,0x28e82ade,0xad65ac6a,0x9bdba1e4,0x2b5f2a63,0x1fdb25e4,0xaf59ae5f,0xac79ad2a,0x24201d7f,0x30743122,0xa81fa17f,
  0xaa31ab91,0x28d026e0,0x2e2d2f8b,0xacceaade,0xa6e0a8d0,0x2b912a31,0x2ade2cce,0xaf8bae2d,0x9d7fa420,0x2d2a2c79,0x217f281f,0xb122b074,
  0xadc2aea7,0x254d1f12,0x31b63294,0xa94da311,0xabf6acde,0x2a31286b,0x2fef30d7,0xae2dac6a,0xa86baa31,0x2cde2bf6,0x2c6a2e2d,0xb0d7afef,
  0x9f12a54d,0x2ea72dc2,0x2311294d,0xb294b1b6,0xaf0cb012,0x267b2052,0x32f73402,0xaa7aa452,0xacdeadf5,0x2b912967,0x30d731e8,0xaf8bad65,
  0xa967ab91,0x2df52cde,0x2d652f8b,0xb1e8b0d7,0xa052a67b,0x30122f0c,0x24522a7a,0xb402b2f7,0xb02cb0d2,0x27a9211b,0x341a34b7,0xaba7a51b,
  0xadc2af0c,0x2c792a63,0x31b632f7,0xb074ae5f,0xaa63ac79,0x2f0c2dc2,0x2e5f3074,0xb2f7b1b6,0xa11ba7a9,0x30d2302c,0x251b2ba7,0xb4b7b41a,
  0xb0d2b194,0x286b21e4,0x34b7356a,0xac6aa5e4,0xaea7b012,0x2d2a2b5f,0x32943402,0xb122af59,0xab5fad2a,0x30122ea7,0x2f593122,0xb402b294,
  0xa1e4a86b,0x319430d2,0x25e42c6a,0xb56ab4b7,0xb17ab257,0x290222ad,0x3552361a,0xad00a6ad,0xaf8cb09f,0x2ddc2c2e,0x33713487,0xb1cfb029,
  0xac2eaddc,0x309f2f8c,0x302931cf,0xb487b371,0xa2ada902,0x3257317a,0x26ad2d00,0xb61ab552,0xb223b31c,0x29992376,0x35eb36c6,0xad97a776,
  0xb039b12d,0x2e8d2cac,0x3426350b,0xb27cb0a6,0xacacae8d,0x312d3039,0x30a6327c,0xb50bb426,0xa376a999,0x331c3223,0x27762d97,0xb6c6b5eb,
  0xb2cdb3e3,0x2a312420,0x3682376f,0xae2da81f,0xb0acb1bb,0x2f3f2d2a,0x3493358d,0xb328b122,0xad2aaf3f,0x31bb30ac,0x31223328,0xb58db493,
  0xa420aa31,0x33e332cd,0x281f2e2d,0xb76fb682,0xb378b456,0x2ac82484,0x3715380a,0xaec3a884,0xb120b24a,0x2ff22da9,0x34ff360e,0xb3d3b19e,
  0xada9aff2,0x324a3120,0x319e33d3,0xb60eb4ff,0xa484aac8,0x34563378,0x28842ec3,0xb80ab715,0xb413b4bc,0x2b5f24e9,0x37a6385a,0xaf59a8e8,
  0xb194b2da,0x30522e28,0x356a368d,0xb43eb219,0xae28b052,0x32da3194,0x3219343e,0xb68db56a,0xa4e9ab5f,0x34bc3413,0x28e82f59,0xb85ab7a6,
  0xb46ab523,0x2bf6254d,0x381a38a8,0xafefa94d,0xb209b36b,0x30ac2ea7,0x35d4370a,0xb493b294,0xaea7b0ac,0x336b3209,0x32943493,0xb70ab5d4,
  0xa54dabf6,0x3523346a,0x294d2fef,0xb8a8b81a,0xb4c3b58c,0x2c4725b2,0x385f38f3,0xb042a9b1,0xb27eb3fd,0x31062f26,0x363c3785,0xb4e7b30f,
  0xaf26b106,0x33fd327e,0x330f34e7,0xb785b63c,0xa5b2ac47,0x358c34c3,0x29b13042,0xb8f3b85f,0xb51cb5f6,0x2c932617,0x38a3393c,0xb08daa16,
  0xb2f4b448,0x31602fa5,0x36a437fe,0xb53ab389,0xafa5b160,0x344832f4,0x3389353a,0xb7feb6a4,0xa617ac93,0x35f6351c,0x2a16308d,0xb93cb8a3,
};
__device__ __align__(128) const uint32_t c_img[2560] = {
  0x326d31ed,0x333b32dd,0x33c33388,0x33fe33ea,0x33c331ed,0x31ed33c3,0xa8b22d64,0xb33bb0c4,0x33ea31ed,0xad64301d,0xb2ddb388,0x315fa8b2,
  0x32dd31ed,0xb3feabc6,0x326dad64,0xad64326d,0x30c431ed,0xaed7b2dd,0x2bc63388,0xa248b3ea,0x2bc631ed,0x315fb3c3,0xb3ea2d64,0x2ed730c4,
  0xa8b231ed,0x3388b01d,0x301db388,0xb1ed28b2,0xb01d31ed,0x22482bc6,0x30c4ad64,0x3388b26d,0x33ea33fe,0x338833c3,0x32dd333b,0x31ed326d,
  0xb2ddb3fe,0xa248b01d,0x326d2ed7,0x338833ea,0x30c433fe,0xb33babc6,0xabc6b33b,0x33fe30c4,0xabc6b3fe,0x31ed32dd,0xb3eaaed7,0x333ba8b2,
  0xa8b233fe,0x2d64b3c3,0xb01d333b,0x315fb26d,0x301db3fe,0xb3fe301d,0x30c42ed7,0x2d64b3ea,0xb26d33fe,0x2ed72bc6,0x33c3b33b,0xa248b0c4,
  0x33c3b3fe,0x315fb2dd,0x28b2aed7,0xaed728b2,0xb0c4b15f,0xaed7b01d,0xabc6ad64,0xa248a8b2,0xabc6b15f,0x315f2bc6,0x33ea3388,0x2ed7326d,
  0x28b2b15f,0x338832dd,0xb01d2d64,0xb1edb3ea,0x301db15f,0x224833c3,0xb0c4b388,0x338830c4,0x326db15f,0xb33b301d,0x33c3ad64,0xb3fe28b2,
  0x33c3b15f,0xb1edabc6,0xa8b23388,0x333bb26d,0x33eab15f,0x2d64b2dd,0xb2dd2d64,0xb15f33ea,0x32ddb15f,0x33feb3c3,0x326db388,0x2d64b0c4,
  0x28b22248,0x2d642bc6,0x301d2ed7,0x315f30c4,0xb01da248,0xb3feb2dd,0xb0c4b33b,0x2d64a8b2,0x326d2248,0x2ed733c3,0xb3c3aed7,0xa248b26d,
  0xb3c3a248,0x315fb01d,0xa8b2333b,0xaed7b3ea,0x33ea2248,0xb388abc6,0x32dd2ed7,0xb1edb0c4,0xb2dda248,0x224832dd,0x326db33b,0xb38828b2,
  0x30c42248,0x333bb3c3,0xabc6aed7,0xb3fe326d,0xabc6a248,0xb1ed301d,0xb3ea333b,0xb33b33ea,0xb26d31ed,0xb33b32dd,0xb3c33388,0xb3fe33ea,
  0xb3c331ed,0xb1ed33c3,0x28b22d64,0x333bb0c4,0xb3ea31ed,0x2d64301d,0x32ddb388,0xb15fa8b2,0xb2dd31ed,0x33feabc6,0xb26dad64,0x2d64326d,
  0xb0c431ed,0x2ed7b2dd,0xabc63388,0x2248b3ea,0xabc631ed,0xb15fb3c3,0x33ea2d64,0xaed730c4,0x28b231ed,0xb388b01d,0xb01db388,0x31ed28b2,
  0x301d31ed,0xa2482bc6,0xb0c4ad64,0xb388b26d,0xb3ea33fe,0xb38833c3,0xb2dd333b,0xb1ed326d,0x32ddb3fe,0x2248b01d,0xb26d2ed7,0xb38833ea,
  0xb0c433fe,0x333babc6,0x2bc6b33b,0xb3fe30c4,0x2bc6b3fe,0xb1ed32dd,0x33eaaed7,0xb33ba8b2,0x28b233fe,0xad64b3c3,0x301d333b,0xb15fb26d,
  0xb01db3fe,0x33fe301d,0xb0c42ed7,0xad64b3ea,0x326d33fe,0xaed72bc6,0xb3c3b33b,0x2248b0c4,0xb3c3b3fe,0xb15fb2dd,0xa8b2aed7,0x2ed728b2,
  0x30c4b15f,0x2ed7b01d,0x2bc6ad64,0x2248a8b2,0x2bc6b15f,0xb15f2bc6,0xb3ea3388,0xaed7326d,0xa8b2b15f,0xb38832dd,0x301d2d64,0x31edb3ea,
  0xb01db15f,0xa24833c3,0x30c4b388,0xb38830c4,0xb26db15f,0x333b301d,0xb3c3ad64,0x33fe28b2,0xb3c3b15f,0x31edabc6,0x28b23388,0xb33bb26d,
  0xb3eab15f,0xad64b2dd,0x32dd2d64,0x315f33ea,0xb2ddb15f,0xb3feb3c3,0xb26db388,0xad64b0c4,0xa8b22248,0xad642bc6,0xb01d2ed7,0xb15f30c4,
  0x301da248,0x33feb2dd,0x30c4b33b,0xad64a8b2,0xb26d2248,0xaed733c3,0x33c3aed7,0x2248b26d,0x33c3a248,0xb15fb01d,0x28b2333b,0x2ed7b3ea,
  0xb3ea2248,0x3388abc6,0xb2dd2ed7,0x31edb0c4,0x32dda248,0xa24832dd,0xb26db33b,0x338828b2,0xb0c42248,0xb33bb3c3,0x2bc6aed7,0x33fe326d,
  0x2bc6a248,0x31ed301d,0x33ea333b,0x333b33ea,0x30c4315f,0x2ed7301d,0x2bc62d64,0x224828b2,0x2bc6315f,0xb15fabc6,0xb3eab388,0xaed7b26d,
  0xa8b2315f,0xb388b2dd,0x301dad64,0x31ed33ea,0xb01d315f,0xa248b3c3,0x30c43388,0xb388b0c4,0xb26d315f,0x333bb01d,0xb3c32d64,0x33fea8b2,
  0xb3c3315f,0x31ed2bc6,0x28b2b388,0xb33b326d,0xb3ea315f,0xad6432dd,0x32ddad64,0x315fb3ea,0xb2dd315f,0xb3fe33c3,0xb26d3388,0xad6430c4,
  0xa8b2a248,0xad64abc6,0xb01daed7,0xb15fb0c4,0x301d2248,0x33fe32dd,0x30c4333b,0xad6428b2,0xb26da248,0xaed7b3c3,0x33c32ed7,0x2248326d,
  0x33c32248,0xb15f301d,0x28b2b33b,0x2ed733ea,0xb3eaa248,0x33882bc6,0xb2ddaed7,0x31ed30c4,0x32dd2248,0xa248b2dd,0xb26d333b,0x3388a8b2,
  0xb0c4a248,0xb33b33c3,0x2bc62ed7,0x33feb26d,0x2bc62248,0x31edb01d,0x33eab33b,0x333bb3ea,0x326d31ed,0x333b32dd,0x33c33388,0x33fe33ea,
  0x33c331ed,0x31ed33c3,0xa8b22d64,0xb33bb0c4,0x33ea31ed,0xad64301d,0xb2ddb388,0x315fa8b2,0x32dd31ed,0xb3feabc6,0x326dad64,0xad64326d,
  0x30c431ed,0xaed7b2dd,0x2bc63388,0xa248b3ea,0x2bc631ed,0x315fb3c3,0xb3ea2d64,0x2ed730c4,0xa8b231ed,0x3388b01d,0x301db388,0xb1ed28b2,
  0xb01d31ed,0x22482bc6,0x30c4ad64,0x3388b26d,0x33ea33fe,0x338833c3,0x32dd333b,0x31ed326d,0xb2ddb3fe,0xa248b01d,0x326d2ed7,0x338833ea,
  0x30c433fe,0xb33babc6,0xabc6b33b,0x33fe30c4,0xabc6b3fe,0x31ed32dd,0xb3eaaed7,0x333ba8b2,0xa8b233fe,0x2d64b3c3,0xb01d333b,0x315fb26d,
  0x301db3fe,0xb3fe301d,0x30c42ed7,0x2d64b3ea,0xb26d33fe,0x2ed72bc6,0x33c3b33b,0xa248b0c4,0x33c3b3fe,0x315fb2dd,0x28b2aed7,0xaed728b2,
  0xb0c4315f,0xaed7301d,0xabc62d64,0xa24828b2,0xabc6315f,0x315fabc6,0x33eab388,0x2ed7b26d,0x28b2315f,0x3388b2dd,0xb01dad64,0xb1ed33ea,
  0x301d315f,0x2248b3c3,0xb0c43388,0x3388b0c4,0x326d315f,0xb33bb01d,0x33c32d64,0xb3fea8b2,0x33c3315f,0xb1ed2bc6,0xa8b2b388,0x333b326d,
  0x33ea315f,0x2d6432dd,0xb2ddad64,0xb15fb3ea,0x32dd315f,0x33fe33c3,0x326d3388,0x2d6430c4,0x28b2a248,0x2d64abc6,0x301daed7,0x315fb0c4,
  0xb01d2248,0xb3fe32dd,0xb0c4333b,0x2d6428b2,0x326da248,0x2ed7b3c3,0xb3c32ed7,0xa248326d,0xb3c32248,0x315f301d,0xa8b2b33b,0xaed733ea,
  0x33eaa248,0xb3882bc6,0x32ddaed7,0xb1ed30c4,0xb2dd2248,0x2248b2dd,0x326d333b,0xb388a8b2,0x30c4a248,0x333b33c3,0xabc62ed7,0xb3feb26d,
  0xabc62248,0xb1edb01d,0xb3eab33b,0xb33bb3ea,0xb26d31ed,0xb33b32dd,0xb3c33388,0xb3fe33ea,0xb3c331ed,0xb1ed33c3,0x28b22d64,0x333bb0c4,
  0xb3ea31ed,0x2d64301d,0x32ddb388,0xb15fa8b2,0xb2dd31ed,0x33feabc6,0xb26dad64,0x2d64326d,0xb0c431ed,0x2ed7b2dd,0xabc63388,0x2248b3ea,
  0xabc631ed,0xb15fb3c3,0x33ea2d64,0xaed730c4,0x28b231ed,0xb388b01d,0xb01db388,0x31ed28b2,0x301d31ed,0xa2482bc6,0xb0c4ad64,0xb388b26d,
  0xb3ea33fe,0xb38833c3,0xb2dd333b,0xb1ed326d,0x32ddb3fe,0x2248b01d,0xb26d2ed7,0xb38833ea,0xb0c433fe,0x333babc6,0x2bc6b33b,0xb3fe30c4,
  0x2bc6b3fe,0xb1ed32dd,0x33eaaed7,0xb33ba8b2,0x28b233fe,0xad64b3c3,0x301d333b,0xb15fb26d,0xb01db3fe,0x33fe301d,0xb0c42ed7,0xad64b3ea,
  0x326d33fe,0xaed72bc6,0xb3c3b33b,0x2248b0c4,0xb3c3b3fe,0xb15fb2dd,0xa8b2aed7,0x2ed728b2,0x29ed29ed,0x29ed29ed,0x29ed29ed,0x29ed29ed,
  0x2bc32a6d,0x2add2bea,0x23c628c4,0xa81da0b2,0x2bc32add,0xa3c6281d,0xabc3aadd,0x23c6a81d,0x29ed2b3b,0xabfea564,0x295fa6d7,0x1a482b88,
  0x25642b88,0xa564ab88,0x25642b88,0xa564ab88,0xa0b22bc3,0x2a6daadd,0xabea23c6,0x28c4281d,0xa8c42bea,0x2a6da0b2,0x28c4abea,0xaa6d20b2,
  0xab3b2bfe,0xa564295f,0x26d79a48,0x2b88a9ed,0x29ed29ed,0x29ed29ed,0x29ed29ed,0x29ed29ed,0xabc3aa6d,0xaaddabea,0xa3c6a8c4,0x281d20b2,
  0x2bc32add,0xa3c6281d,0xabc3aadd,0x23c6a81d,0xa9edab3b,0x2bfe2564,0xa95f26d7,0x9a48ab88,0x25642b88,0xa564ab88,0x25642b88,0xa564ab88,
  0x20b2abc3,0xaa6d2add,0x2beaa3c6,0xa8c4a81d,0xa8c42bea,0x2a6da0b2,0x28c4abea,0xaa6d20b2,0x2b3babfe,0x2564a95f,0xa6d71a48,0xab8829ed,
  0x295f295f,0x295f295f,0x295f295f,0x295f295f,0x23c628c4,0xa81da0b2,0xabc3aa6d,0xaaddabea,0xa3c6281d,0xabc3aadd,0x23c6a81d,0x2bc32add,
  0xa95f26d7,0x9a48ab88,0x29ed2b3b,0xabfea564,0xab882564,0x2b88a564,0xab882564,0x2b88a564,0xabea23c6,0x28c4281d,0x20b2abc3,0xaa6d2add,
  0xaa6d20b2,0xa8c42bea,0x2a6da0b2,0x28c4abea,0xa6d71a48,0xab8829ed,0xab3b2bfe,0xa564295f,0x295f295f,0x295f295f,0x295f295f,0x295f295f,
  0xa3c6a8c4,0x281d20b2,0x2bc32a6d,0x2add2bea,0xa3c6281d,0xabc3aadd,0x23c6a81d,0x2bc32add,0x295fa6d7,0x1a482b88,0xa9edab3b,0x2bfe2564,
  0xab882564,0x2b88a564,0xab882564,0x2b88a564,0x2beaa3c6,0xa8c4a81d,0xa0b22bc3,0x2a6daadd,0xaa6d20b2,0xa8c42bea,0x2a6da0b2,0x28c4abea,
  0x26d79a48,0x2b88a9ed,0x2b3babfe,0x2564a95f,0xabfe2bfe,0xabfe2bfe,0xabfe2bfe,0xabfe2bfe,0xaadd2bea,0xa3c628c4,0x281da0b2,0x2bc3aa6d,
  0xa81d2bc3,0x2adda3c6,0x281dabc3,0xaadd23c6,0x9a482b88,0x29edab3b,0xabfe2564,0x295f26d7,0x26d72b3b,0xa6d7ab3b,0x26d72b3b,0xa6d7ab3b,
  0x2a6d2add,0xabeaa3c6,0x28c4a81d,0x20b22bc3,0x2bea2a6d,0xa0b228c4,0xabeaaa6d,0x20b2a8c4,0x2b8829ed,0x2b3b2bfe,0x2564295f,0xa6d79a48,
  0xabfe2bfe,0xabfe2bfe,0xabfe2bfe,0xabfe2bfe,0x2addabea,0x23c6a8c4,0xa81d20b2,0xabc32a6d,0xa81d2bc3,0x2adda3c6,0x281dabc3,0xaadd23c6,
  0x1a48ab88,0xa9ed2b3b,0x2bfea564,0xa95fa6d7,0x26d72b3b,0xa6d7ab3b,0x26d72b3b,0xa6d7ab3b,0xaa6daadd,0x2bea23c6,0xa8c4281d,0xa0b2abc3,
  0x2bea2a6d,0xa0b228c4,0xabeaaa6d,0x20b2a8c4,0xab88a9ed,0xab3babfe,0xa564a95f,0x26d71a48,0x1a489a48,0x1a489a48,0x1a489a48,0x1a489a48,
  0x281da0b2,0x2bc3aa6d,0x2addabea,0x23c6a8c4,0x2adda3c6,0x281dabc3,0xaadd23c6,0xa81d2bc3,0x2bfea564,0xa95fa6d7,0x9a482b88,0x29edab3b,
  0x2b3ba6d7,0xab3b26d7,0x2b3ba6d7,0xab3b26d7,0x28c4a81d,0x20b22bc3,0xaa6daadd,0x2bea23c6,0x20b2a8c4,0x2bea2a6d,0xa0b228c4,0xabeaaa6d,
  0xa564a95f,0x26d71a48,0x2b8829ed,0x2b3b2bfe,0x1a489a48,0x1a489a48,0x1a489a48,0x1a489a48,0xa81d20b2,0xabc32a6d,0xaadd2bea,0xa3c628c4,
  0x2adda3c6,0x281dabc3,0xaadd23c6,0xa81d2bc3,0xabfe2564,0x295f26d7,0x1a48ab88,0xa9ed2b3b,0x2b3ba6d7,0xab3b26d7,0x2b3ba6d7,0xab3b26d7,
  0xa8c4281d,0xa0b2abc3,0x2a6d2add,0xabeaa3c6,0x20b2a8c4,0x2bea2a6d,0xa0b228c4,0xabeaaa6d,0x2564295f,0xa6d79a48,0xab88a9ed,0xab3babfe,
  0xa95fa95f,0xa95fa95f,0xa95fa95f,0xa95fa95f,0xa3c6a8c4,0x281d20b2,0x2bc32a6d,0x2add2bea,0x23c6a81d,0x2bc32add,0xa3c6281d,0xabc3aadd,
  0x295fa6d7,0x1a482b88,0xa9edab3b,0x2bfe2564,0x2b88a564,0xab882564,0x2b88a564,0xab882564,0x2beaa3c6,0xa8c4a81d,0xa0b22bc3,0x2a6daadd,
  0x2a6da0b2,0x28c4abea,0xaa6d20b2,0xa8c42bea,0x26d79a48,0x2b88a9ed,0x2b3babfe,0x2564a95f,0xa95fa95f,0xa95fa95f,0xa95fa95f,0xa95fa95f,
  0x23c628c4,0xa81da0b2,0xabc3aa6d,0xaaddabea,0x23c6a81d,0x2bc32add,0xa3c6281d,0xabc3aadd,0xa95f26d7,0x9a48ab88,0x29ed2b3b,0xabfea564,
  0x2b88a564,0xab882564,0x2b88a564,0xab882564,0xabea23c6,0x28c4281d,0x20b2abc3,0xaa6d2add,0x2a6da0b2,0x28c4abea,0xaa6d20b2,0xa8c42bea,
  0xa6d71a48,0xab8829ed,0xab3b2bfe,0xa564295f,0x29ed29ed,0x29ed29ed,0x29ed29ed,0x29ed29ed,0x2bc32a6d,0x2add2bea,0x23c628c4,0xa81da0b2,
  0x2bc32add,0xa3c6281d,0xabc3aadd,0x23c6a81d,0x29ed2b3b,0xabfea564,0x295fa6d7,0x1a482b88,0x25642b88,0xa564ab88,0x25642b88,0xa564ab88,
  0xa0b22bc3,0x2a6daadd,0xabea23c6,0x28c4281d,0xa8c42bea,0x2a6da0b2,0x28c4abea,0xaa6d20b2,0xab3b2bfe,0xa564295f,0x26d79a48,0x2b88a9ed,
  0x29ed29ed,0x29ed29ed,0x29ed29ed,0x29ed29ed,0xabc3aa6d,0xaaddabea,0xa3c6a8c4,0x281d20b2,0x2bc32add,0xa3c6281d,0xabc3aadd,0x23c6a81d,
  0xa9edab3b,0x2bfe2564,0xa95f26d7,0x9a48ab88,0x25642b88,0xa564ab88,0x25642b88,0xa564ab88,0x20b2abc3,0xaa6d2add,0x2beaa3c6,0xa8c4a81d,
  0xa8c42bea,0x2a6da0b2,0x28c4abea,0xaa6d20b2,0x2b3babfe,0x2564a95f,0xa6d71a48,0xab8829ed,0x9a481a48,0x9a481a48,0x9a481a48,0x9a481a48,
  0xa81d20b2,0xabc32a6d,0xaadd2bea,0xa3c628c4,0xaadd23c6,0xa81d2bc3,0x2adda3c6,0x281dabc3,0xabfe2564,0x295f26d7,0x1a48ab88,0xa9ed2b3b,
  0xab3b26d7,0x2b3ba6d7,0xab3b26d7,0x2b3ba6d7,0xa8c4281d,0xa0b2abc3,0x2a6d2add,0xabeaa3c6,0xa0b228c4,0xabeaaa6d,0x20b2a8c4,0x2bea2a6d,
  0x2564295f,0xa6d79a48,0xab88a9ed,0xab3babfe,0x9a481a48,0x9a481a48,0x9a481a48,0x9a481a48,0x281da0b2,0x2bc3aa6d,0x2addabea,0x23c6a8c4,
  0xaadd23c6,0xa81d2bc3,0x2adda3c6,0x281dabc3,0x2bfea564,0xa95fa6d7,0x9a482b88,0x29edab3b,0xab3b26d7,0x2b3ba6d7,0xab3b26d7,0x2b3ba6d7,
  0x28c4a81d,0x20b22bc3,0xaa6daadd,0x2bea23c6,0xa0b228c4,0xabeaaa6d,0x20b2a8c4,0x2bea2a6d,0xa564a95f,0x26d71a48,0x2b8829ed,0x2b3b2bfe,
  0xabfe2bfe,0xabfe2bfe,0xabfe2bfe,0xabfe2bfe,0xaadd2bea,0xa3c628c4,0x281da0b2,0x2bc3aa6d,0xa81d2bc3,0x2adda3c6,0x281dabc3,0xaadd23c6,
  0x9a482b88,0x29edab3b,0xabfe2564,0x295f26d7,0x26d72b3b,0xa6d7ab3b,0x26d72b3b,0xa6d7ab3b,0x2a6d2add,0xabeaa3c6,0x28c4a81d,0x20b22bc3,
  0x2bea2a6d,0xa0b228c4,0xabeaaa6d,0x20b2a8c4,0x2b8829ed,0x2b3b2bfe,0x2564295f,0xa6d79a48,0xabfe2bfe,0xabfe2bfe,0xabfe2bfe,0xabfe2bfe,
  0x2addabea,0x23c6a8c4,0xa81d20b2,0xabc32a6d,0xa81d2bc3,0x2adda3c6,0x281dabc3,0xaadd23c6,0x1a48ab88,0xa9ed2b3b,0x2bfea564,0xa95fa6d7,
  0x26d72b3b,0xa6d7ab3b,0x26d72b3b,0xa6d7ab3b,0xaa6daadd,0x2bea23c6,0xa8c4281d,0xa0b2abc3,0x2bea2a6d,0xa0b228c4,0xabeaaa6d,0x20b2a8c4,
  0xab88a9ed,0xab3babfe,0xa564a95f,0x26d71a48,0x3bfb3bff,0x3be53bf2,0x3bbf3bd4,0x3b873ba5,0x3bd03bfb,0x3b013b7c,0x399d3a60,0x378538bc,
  0x3a543bcf,0x2884374e,0xb9f8b648,0xbbe9bbab,0x398b3bb7,0xb4db3340,0xbbdcb9fc,0xb911bb85,0x35173b52,0xbbc9b7c8,0xb074ba9b,0x3bfe391b,
  0x319e3b27,0xbbf3b979,0x363cb80a,0x3a2d3bc5,0xb4323a8c,0xb6a4bbf9,0x3b3539b8,0xbbc3ae91,0xb66b3a50,0xad65bbe4,0x38653b90,0xbb0db966,
  0xac6aa5e4,0xb122af59,0xb402b294,0xb56ab4b7,0xb2deac9c,0xb7bdb5a5,0xb9b3b8d6,0xbb10ba73,0xb8e5b2f7,0xbbffbb1e,0xb954bb5c,0x30beb493,
  0xb9c5b43e,0xbb9fbbcb,0xb201b94f,0x3a313576,0xbb96b676,0xb359bafe,0x3bec3884,0x2a163a29,0xbbe0b72c,0x2f27b9d6,0x3b5e3ae8,0xb91633a2,
  0xbbb8b899,0x3b47ad33,0xb6f43999,0xb3babbf5,0xbb54b8ea,0x3bf9313b,0xbab0353a,0x3790b9e7,0x3b3f3b65,0x3ae83b16,0x3a813ab6,0x3a0d3a49,
  0x3263356a,0xad972b43,0xb5dfb359,0xb8eeb7f3,0xb825baa9,0x353aaec3,0x3b7c3994,0x3af43bfa,0x360eb0be,0x3bf43a64,0x388e3b47,0xb7372c6a,
  0xa9b139aa,0xbbedba25,0x3340b889,0x3b983afb,0xbaa2aa16,0xb4cfbb8e,0x3c0038ad,0xb44b38e5,0x38bcb874,0x2ba73bac,0xb979bb59,0x3bf03742,
  0x3c0033ba,0xbb043402,0x3855b974,0xacce3b96,0xb6c6b61a,0xb80ab76f,0xb8a8b85a,0xb93cb8f3,0xbbd7bb87,0xbbf8bbfd,0xbb71bbc9,0xba4dbaf1,
  0x3ad8386f,0x3b903bf5,0x35a539bc,0xb7e8ad00,0x3b683be9,0x2ef538d1,0xba93b6a4,0xbb24bbfb,0xbbfeb9a6,0x305bb91f,0x3bcb3a97,0xb50b37d2,
  0xb87abbfe,0x3ba13546,0x24523a7e,0xbbb5ba54,0x3a733aa5,0xbbfcb487,0x39d6b654,0xafef3b21,0x1cb63bc3,0xb7b2bbbf,0x3aba39da,0xbbfab517,
  0x398b39cd,0x38fd3946,0x386538b2,0x37853815,0xba85b9c9,0xbb92bb1e,0xbbfebbdd,0xbbc2bbf5,0x319e389e,0xb929b426,0xbc00bb45,0xb911bb37,
  0xbbffbac1,0xb805bafe,0x382a217f,0x3bfd3b13,0xb66b3682,0xbb01bb94,0x387fb371,0x3a2d3beb,0xbac7bb76,0x3a00ad33,0x36bb3bd4,0xbbeab79b,
  0xbabd330f,0x34dbba58,0x36023bfe,0xbb0db9f4,0xb68dbbe1,0x3a5c3a45,0xbbe7b648,0x3b89adfb,0xb9c5b982,0xba41ba04,0xbab0ba7a,0xbb10bae1,
  0xb8a3b986,0xb52fb74e,0xa94db1e8,0x33d32e91,0xbbe0ba89,0xba1dbbba,0x1fdbb6af,0x3a3136e8,0xa776b84a,0x3aeb37c8,0x3ad53c00,0xaa7a377a,
  0xbb54bb4f,0x37bdb523,0x3a9e3bc8,0xb916308d,0x3840b5c8,0x394a3bf9,0xbb42b294,0xb0a6bb0a,0xb850bbce,0x3b9f38e0,0xbb6a28e8,0x3790b958,
  0x3b4cb185,0xb8db38f8,0x30f0bb5c,0x355e3bf7,0x363136dd,0x34cf3581,0x32c6341a,0x2fbd3153,0xbae1bb65,0xb970ba39,0xb715b889,0xb16cb4f3,
  0x3219b3d3,0x3b0438b7,0x3b713bfc,0x34ff397d,0x36e83aa9,0xb8b2adc9,0xbbefbb59,0xb5bcba49,0xb9a12a7a,0xb924bbfe,0x3a933042,0x37dd3bcc,
  0x308db9aa,0x3b453b07,0xb94632ad,0xb845bbfa,0x3bd730a6,0xb902382a,0xa452bb92,0x39373b7a,0xb9583874,0x3371bb16,0x34263c00,0xb982bafb,
  0xbb60bb3a,0xbba1bb83,0xbbd2bbbc,0xbbf1bbe3,0x3815361a,0x39df3907,0x3b2c3a97,0x3be23b9c,0x3bda3bc2,0x37b23a76,0xb5df2c06,0xbb9ab9d2,
  0xbb37b86f,0xba7abbf8,0x3029b654,0x3b7838f3,0xb9afbbfd,0x3a21294d,0x388e3bee,0xbaf7b328,0x3beb39a6,0xb6af37a6,0xba04bbd3,0x3ac42d00,
  0x32633bea,0xba3dbad5,0x3c00352f,0xba1135b1,0xb9f4baa5,0x3bc8376f,0xbbba2311,0x39cdb7d2,0x3b7a3bf1,0x394a3a93,0x33893764,0xb3d39cb6,
  0x3afb3be2,0x35eb3946,0xb4c328e8,0xbaa9b8cc,0x38a33b9a,0xb8dba452,0xbb83bbae,0x2a7ab86a,0x37423b78,0xbab6b426,0xb907bbe6,0x39aa2ade,
  0x27763af7,0xbb2fbaba,0x3a76ad97,0x30a63b60,0xaf8b3ac4,0xb994bb94,0x3bf8358d,0xb8743815,0xb8403a11,0x341abb57,0x294d3bf4,0xb55ebbda,
  0xb93339cd,0x3889ba58,0xb7a63ad1,0x3625bb37,0xb5b1afbd,0xba00b88e,0xbbc6bb18,0xbbc2bc00,0xb7d2b16c,0xbb6fba04,0xbba3bbfe,0xb86fba67,
  0xba85b4ff,0xba5cbc00,0x3581b47b,0x3bfd3aac,0xbb21b5bc,0xb85abbba,0x3a393109,0x39a63bfd,0xbbffb7dd,0x370ab855,0x38b73bf8,0xbbeab631,
  0xbbf2b845,0x39bcb523,0x2dc93b81,0xbaa5bae1,0xbac7b937,0x3bbc365f,0xbbfeaef5,0x3b89b219,0xba15b982,0x3a9738e0,0xbb07b830,0x3b6336e8,
  0xb958b785,0xbb81ba9e,0xbbefbbf3,0xba89bb73,0xbbf7bbc2,0xb9b8bb42,0xaf59b70a,0x384a3328,0x3bc03911,0x38303b6a,0xb946ad65,0xbb4fbbd0,
  0x3a353bfd,0xb85f30f0,0xbb1ebbbc,0x35c8b5b1,0xbb8bba2d,0x39dfb27c,0x34263bb0,0xbbceb98b,0xb4b7bbea,0x3b6c39e3,0xbafe2c06,0x3185ba85,
  0x38cc3b0d,0xba7ab99d,0x3b943759,0xbbffb19e,0xb4933b89,0x31e8bbc6,0xad333bee,0xa5e4bbff,0xb9f4bb10,0xb58db87f,0x3029af27,0x389e35d4,
  0x2dfbb3d3,0x399936bb,0x3bf23b2f,0x3ac13bcc,0x33eb3a31,0xbad1b602,0xba04bbf9,0x3682b2de,0xb90c2a7a,0xbab3bbe7,0x374eb41a,0x3b763b7a,
  0x3552b916,0x39703bd6,0xbbbab46f,0x330fb9c5,0x3ba530a6,0xb5f7396b,0xb7c8bbfc,0x3be138a3,0xba673790,0x38b2b9b3,0xb5233b1b,0x26adbbe0,
  0xbbabb55e,0x3bdd3389,0xbbf9b042,0x3bff2776,0xb742b93c,0x2311b340,0x37a6340e,0x3aa93966,0x3b963a4d,0x3b7f3c00,0x380f3a21,0xb0be3219,
  0x2f8bb7e8,0x3bde3979,0x376f3b32,0xb9aab0d7,0x3bb83b24,0xb1223855,0xbbfdba3d,0xaa16b9a1,0x3933b50b,0x35eb3be4,0xbbf5b8d6,0x3874b6c6,
  0x39413bb5,0xbbffb65f,0x38d1b764,0x33ba3bd7,0x3bb3afef,0xbab63699,0x391fb94f,0xb6253ad8,0x30103bfa,0xb359bbdf,0x35463bae,0xb6d2bb68,
  0x3b213a0d,0x3c003bcb,0x3b073bbd,0x386f39e7,0x351738ee,0xb599a452,0xbae5b924,0xbbe9bbda,0x3bf23af4,0x31cf39d6,0xbb16b6ff,0xb9a6bbe8,
  0xb4323737,0xbbe5baba,0x2b43b902,0x3bfe39af,0x3a153b98,0xbb6fb13b,0x2ec3ba60,0x3aa53b3f,0xba09344b,0xa884bb57,0x3a643b18,0xbbc3b263,
  0x34573bf0,0xb85abb4a,0x3a2539fc,0xbb63b825,0xbbef2cce,0x3bc9b1b6,0xbb8e347b,0x3b3db60e,0x3bf53b87,0x3b6c3bec,0x392e3a7e,0x32f73721,
  0xb9e7b785,0xbbfcbb5e,0xba81bbb0,0xb43eb894,0xbb13bbe9,0x31e8b6f4,0x3bf239da,0x36763af1,0x3be83911,0x340e3ab0,0xbb7cb759,0xb72cbb73,
  0x379b3bfe,0xbc00b80f,0x374eb835,0x38993bfb,0xbb3fba2d,0x3b329fdb,0xb3403a41,0xb8eabbd0,0x2dfbbbc3,0x32943bfd,0xb7c8bb7f,0x39c93a54,
  0x38253b0d,0xb8d6ba9e,0x39793a1d,0xba0db98b,0x2e91356a,0xb5f7b074,0xba19b8ad,0xbbcfbb2a,0xb966bb10,0xaba7b63c,0x38a8346f,0x3bb73a90,
  0x377ab0be,0x3bdd3b35,0x2f593974,0xbb52b7f3,0x30d73a31,0xbbbdb865,0xb5a5bb1b,0x3b2735d4,0xbb0aaa16,0xa17fbae5,0x3b1e3ace,0xba8c2c6a,
  0x36c6b916,0x36ff3c00,0xbbcbb8fd,0x3a50b2de,0x3bf733ba,0xbbd42b43,0x3afeb599,0xb98638e5,0xbad83790,0x3a60b87f,0xb9d63929,0x393cb9c5,
  0xba093986,0x3a7eb8f8,0xbae5385f,0x3b3db77a,0xbabd393c,0x3bb0b699,0xbc00305b,0x3ba730d7,0xbbef384a,0x39da34e7,0x2b43bb6c,0xba6f3b0a,
  0xbc0037e8,0x3759383a,0x387fbbfc,0xbbf636c6,0xbb2a35c8,0xb8353bb2,0x3a64b1e8,0x3962bbf7,0xba90350b,0xba413bff,0x3602340e,0x3bf6bad8,
  0xb7f33185,0xbb7f3a19,0xbb8e3c00,0xb8203a35,0xb5d42fef,0xba1d38a8,0xbbd63b32,0xbba93bfe,0xb941b9c9,0x38ad3a45,0xb80fbab3,0x36d23b13,
  0xb850ba0d,0x346f3b4a,0x1fdbbbed,0xb4ab3be8,0xb010bac1,0xb9743b9e,0x3bfdb5f7,0xb8c1b79b,0x251bbaf4,0xbb1b3acb,0x3a9e2ba7,0x2e5fbb3f,
  0x3721bb76,0xbace3463,0xb8d13bdd,0x39ebadfb,0x3894bb98,0xb8fd281f,0xbb6a3bbd,0x2e2d3825,0x3af1bbe1,0x3599b92e,0xb546a17f,0xbadb390c,
  0x3b73bbf0,0x3929ba81,0x327cb6ff,0xb49f29b1,0xbb853625,0x3bbdb4c3,0xbbe432ad,0x3bfbaf8b,0xbaacb6d2,0x39243954,0xb65fbace,0x2fbd3bb8,
  0x3bc5b24b,0xb6ffb907,0xb6993c00,0x3bb7b933,0x363138c1,0x3902bbec,0xbbdf3599,0x34ff3941,0xb9661648,0xba603bf8,0x383a31cf,0x3b27bbb3,
  0x3219b9eb,0xbb1836f4,0xb9903be5,0x37dd3010,0x30d73232,0x39fcb7a6,0x3bffbb6f,0x3a50bb9c,0xb9a13adb,0xb47b380f,0x32c62884,0x3937b721,
  0xb576bb63,0x340e3ba3,0xb13bbbd3,0x2c9c3bf2,0x386abb3d,0xba2139f8,0x3b57b835,0xbbf13432,0xb3a23bd8,0x3b32ba39,0xbb4a2311,0x343e3a15,
  0xbb603a6f,0x3a3d3074,0x31b6bb7f,0xbb9a3a09,0x39e7bc00,0xb8d6adc9,0xbacb3bde,0x372c3457,0x3bdab962,0x3764bb35,0xb9c03122,0xbaf73bef,
  0xbbe83bd9,0xb94f3b07,0xa81f35eb,0x38eab4f3,0xb9af3820,0xbbae3ae5,0xbbd23bff,0xba113b2a,0xbc0026ad,0x3bf32c38,0xbbd6b109,0x3ba733eb,
  0x3153bbff,0xb70a3b9e,0x396bba9b,0xbade390c,0xba90b16c,0x2d653aee,0x39b3bb81,0xbbf63552,0x397dbbcf,0xbbbc3463,0x338939b8,0x39f0bba5,
  0xb5d4b5bc,0xbbb03b2c,0x32013830,0x3bf6ba67,0x3bccbb52,0x2c06b92e,0xbb83385f,0xb8c73bab,0x32deb845,0xb7593029,0xbb5e39df,0xbba93bfd,
  0x3b7aba8c,0x3beebbf2,0x3a76bb6c,0x36ddb91b,0x251bbbff,0xaf273bfc,0x327cbbe6,0xb4ab3bc0,0x3be325e4,0xbb2fb4e7,0x39e33884,0xb81aba35,
  0x3894bbe2,0xbbf937fe,0x399d358d,0x2e5fbb8b,0x39d232f7,0x341abbb2,0xbbc63999,0x395d34b7,0x3b73bb78,0xb46fb715,0xbbdc3ad1,0x2e2d38cc,
  0x33283676,0x3bfcba19,0x3581bab3,0xba6b3493,0x3bd0bac4,0x3b1bbbef,0x363cb970,0xb49faade,0xb5b13899,0x30422f59,0x38b7b5f7,0x3b3aba29,
  0xbb68b55e,0x3b1836bb,0xbabab805,0x3a4d38a3,0x3bc0b625,0xbbfe2ec3,0x3b9431cf,0xba89b742,0x387a381a,0x347bbbe7,0xbb573a00,0x3b242776,
  0xbb8b324b,0x31093a25,0x3a58bb6f,0xbb4f2f8b,0x9cb6b95d,0xbbf8396b,0xb1b63a5c,0x3bb5b840,0x38cc9648,0x3b81bbac,0xac38b85a,0xbbce3933,
  0xb86a3a6b,0x2ef53389,0x39c0b70a,0x3bfabb4c,0xaadeb232,0xb83034c3,0xbaee39bc,0xbbff3bb3,0x360ebb89,0xb7643b42,0x3855baeb,0xb8ee3a85,
  0x33eb3b63,0x28e8bbf5,0xb5233bde,0x389ebb21,0xbaa23ade,0x3baeb0f0,0xb65fb94a,0xb7373bff,0x3552bbd8,0xbbe6391f,0x38e035eb,0x3682bbf2,
  0x3c00b9f0,0x2d97b9e3,0xbbdf38db,0xb44b3ac7,0xba673c00,0x358d3487,0x3bfcbab6,0x330fba15,0xbaac38c7,0xbbf43bc6,0xb9903b2f,0xacce368d,
  0x3bfdbbd9,0x3ad1bba3,0x37feb994,0x26adb457,0xbb4c38ee,0x3bfcb1b6,0xbad5b4cf,0x381a39af,0xbbb3389e,0x3b592c38,0xb76fb970,0xb24b3beb,
  0xbbe33737,0x304239c0,0x3b42bb04,0xb95db263,0xbb9c3682,0xb2ad3aee,0x3bf5b8b2,0x1648b9f4,0xb9d2344b,0xbb923bd2,0xb0f03924,0x3a6bb60e,
  0xb8f3330f,0xbc003b2c,0xb91f3b45,0x323233eb,0xb3282cce,0xb80535df,0xb9e33902,0xbb3a3aa2,0xad0026ad,0xb1cf3029,0xb4873371,0xb61a3552,
  0xb68dba4d,0xac063bdf,0x382abba1,0xbade39a1,0xb457ba89,0xb6543bfc,0x3b16b9df,0xbbd8308d,0x3153bb24,0xbbee3990,0x36bb37b2,0x39f0bbd7,
  0x34f3bb4f,0xbbd337fe,0xaec33a7a,0x3c00b958,0x397dbbb5,0xb52fb2c6,0xbbe73a21,0xb8c73b68,0x3a49bbce,0x2311b715,0xba2536af,0xbbd93bc0,
  0x3bccbbfa,0x3aebbb71,0x396bba3d,0x36ddb87a,0x3bfabbff,0x3bdebbef,0x3bacbbc8,0x3b65bb8b,0xaadebba7,0xb6af3bdc,0x3a58ba41,0xbbe2366b,
  0x3a29bade,0xbc003581,0x3a45352f,0xb2f7bac7,0xb8153bf6,0x3bc8b63c,0xac38ba1d,0xbb783abd,0xbbf539f0,0x329438b7,0x3b9ebaeb,0xb676b68d,
  0x3b37bbf6,0x28e8b865,0xbaee37bd,0xbac43c00,0x3b13b8c7,0x3b5cbbfe,0x3463b94a,0xb8993153,0xbbeb3ba9,0xbbe63c00,0xbb2c3b9f,0xb9cd3a90,
  0xb79b36dd,0xb884382a,0xb92e38db,0xb9c9397d,0x3bfdb4ab,0xbb45b201,0x38e038fd,0xb16cbb54,0x391b381a,0xa17fbb83,0xb8f83b92,0x3bcfb840,
  0xbae12e5f,0xb3713b5e,0x3bfcb929,0xb5bcb850,0xae91b95d,0xbbd43a76,0x34e73805,0x3b52bb4c,0x36e82e2d,0x3bfebab0,0x37febb01,0xb845251b,
  0xb77a3a6b,0x3648294d,0x3bb2ba00,0x3a8cbbe3,0x308db49f,0xb1091fdb,0xb71534db,0xb9823894,0x3b0abb3a,0x3a9bbad5,0x3a19ba5c,0x3986b9d2,
  0x3b9c2c9c,0xb994b83a,0x34873ae8,0x324bbbfe,0xb7213bf1,0x3b47b990,0xbbbf2d97,0x38c1387a,0x38f3343e,0x3889bbff,0xbba3353a,0x96483a73,
  0xbaf13b9a,0x38ad32c6,0x39f8bbf4,0xb9eb9cb6,0x2d00372c,0x3b59b8a8,0x3a39bbed,0xb232b576,0xbbfb3af7,0xb9743b71,0x307434cf,0x3adbb86a,
  0xb7d238ea,0xb2ad35a5,0x2dc92ba7,0x361ab3a2,0xba543a11,0xbace3a93,0xbb353b04,0xbb873b60,0xb4f33bfb,0x39bcbacb,0xbbac380a,0x3bd8a9b1,
  0xbb2aafbd,0x36a439c0,0x3402bbf8,0xba6f3aa2,0xba493bb7,0x3a97a81f,0x34c3bb90,0xbc0038bc,0xb7f3b4ff,0xba7e3bd2,0x39542ef5,0x3962bc00,
  0xbbfa3b27,0xb6543a81,0x3907b05b,0x3bd9bb85,0x2c6ab7dd,0xb9da35df,0xbbec3ba1,0xb8203aac,0xbafb3a50,0xbbd33b7c,0xbbf83bfc,0xbb653bc5,
  0x38e5b937,0x3835b88e,0x36f4b7b2,0x356ab631,0xb90c3b3d,0x3b5cb8d1,0xbbf93122,0x3ac13517,0x29b1bba7,0xb94f3b6a,0x3be4b7bd,0xbaf4b19e,
  0x3ba5ba6f,0xb884b546,0xb8f83bff,0x3b76b432,0xb8bc3bf6,0x3ae8b27c,0x3699bb9f,0xbb98366b,0xbbab3962,0xb9993bbf,0x34e73359,0x3be1ba09,
  0x3b85bbf6,0x353ab99d,0xb83a2f27,0xbbf03abd,0x391bb820,0x3ab3b9f8,0x3bb2bb47,0x3bffbbef,0xbbc53ba9,0xbbed3bdc,0xbbff3bf9,0xbbfb3c00,
  0xba35b6d2,0x36483a64,0x2d33bbe5,0xb84a3b96,0x3bfeb4ab,0xb9fcb602,0x313b3b01,0x37e8bbe0,0x34b738c1,0x3a9bbb8e,0xba45a884,0xb5c83bb8,
  0xba732e5f,0xb80a3bd6,0x3b4ab4db,0x350bbb54,0x3493b9eb,0xb9b83402,0xbb9e3bc9,0xb1853941,0x35762e2d,0x3b90b9b3,0x3acbbbf3,0x2fefb850,
  0xba293adb,0xb85f3954,0xb46336a4,0x25e43010,0x33a2b49f,0x305bb201,0x281fad65,0xac9c251b,0x3f803f80,0x3f803f80,0x3f803f80,0x3f803f80,
  0x3f803f80,0x3f803f80,0x3f803f80,0x3f803f80,0x3f803f80,0x3f803f80,0x3f803f80,0x3f803f80,0x3f803f80,0x3f803f80,0x3f803f80,0x3f803f80,
  0x3f803f80,0x3f803f80,0x3f803f80,0x3f803f80,0x3f803f80,0x3f803f80,0x3f803f80,0x3f803f80,0x3f803f80,0x3f803f80,0x3f803f80,0x3f803f80,
  0x3f803f80,0x3f803f80,0x3f803f80,0x3f803f80,0x3f803f80,0x3f803f80,0x3f803f80,0x3f803f80,0x3f803f80,0x3f803f80,0x3f803f80,0x3f803f80,
  0x3f803f80,0x3f803f80,0x3f803f80,0x3f803f80,0x3f803f80,0x3f803f80,0x3f803f80,0x3f803f80,0x3f803f80,0x3f803f80,0x3f803f80,0x3f803f80,
  0x3f803f80,0x3f803f80,0x3f803f80,0x3f803f80,0x3f803f80,0x3f803f80,0x3f803f80,0x3f803f80,0x3f803f80,0x3f803f80,0x3f803f80,0x3f803f80,
  0x3f803f80,0x3f803f80,0x3f803f80,0x3f803f80,0x3f803f80,0x3f803f80,0x3f803f80,0x3f803f80,0x3f803f80,0x3f803f80,0x3f803f80,0x3f803f80,
  0x3f803f80,0x3f803f80,0x3f803f80,0x3f803f80,0x3f803f80,0x3f803f80,0x3f803f80,0x3f803f80,0x3f803f80,0x3f803f80,0x3f803f80,0x3f803f80,
  0x3f803f80,0x3f803f80,0x3f803f80,0x3f803f80,0x3f803f80,0x3f803f80,0x3f803f80,0x3f803f80,0x3f803f80,0x3f803f80,0x3f803f80,0x3f803f80,
  0x3f803f80,0x3f803f80,0x3f803f80,0x3f803f80,0x3f803f80,0x3f803f80,0x3f803f80,0x3f803f80,0x3f803f80,0x3f803f80,0x3f803f80,0x3f803f80,
  0x3f803f80,0x3f803f80,0x3f803f80,0x3f803f80,0x3f803f80,0x3f803f80,0x3f803f80,0x3f803f80,0x3f803f80,0x3f803f80,0x3f803f80,0x3f803f80,
  0x3f803f80,0x3f803f80,0x3f803f80,0x3f803f80,0x3f803f80,0x3f803f80,0x3f803f80,0x3f803f80,0x3f803f80,0x3f803f80,0x3f803f80,0x3f803f80,
  0x3f803f80,0x3f803f80,0x3f803f80,0x3f803f80,0x3f803f80,0x3f803f80,0x3f803f80,0x3f803f80,0x3f803f80,0x3f803f80,0x3f803f80,0x3f803f80,
  0x3f803f80,0x3f803f80,0x3f803f80,0x3f803f80,0x3f803f80,0x3f803f80,0x3f803f80,0x3f803f80,0x3f803f80,0x3f803f80,0x3f803f80,0x3f803f80,
  0x3f803f80,0x3f803f80,0x3f803f80,0x3f803f80,0x3f803f80,0x3f803f80,0x3f803f80,0x3f803f80,0x3f803f80,0x3f803f80,0x3f803f80,0x3f803f80,
  0x3f803f80,0x3f803f80,0x3f803f80,0x3f803f80,0x3f803f80,0x3f803f80,0x3f803f80,0x3f803f80,0x3f803f80,0x3f803f80,0x3f803f80,0x3f803f80,
  0x3f803f80,0x3f803f80,0x3f803f80,0x3f803f80,0x3f803f80,0x3f803f80,0x3f803f80,0x3f803f80,0x3f803f80,0x3f803f80,0x3f803f80,0x3f803f80,
  0x3f803f80,0x3f803f80,0x3f803f80,0x3f803f80,0x3f803f80,0x3f803f80,0x3f803f80,0x3f803f80,0x3f803f80,0x3f803f80,0x3f803f80,0x3f803f80,
  0x3f803f80,0x3f803f80,0x3f803f80,0x3f803f80,0x3f803f80,0x3f803f80,0x3f803f80,0x3f803f80,0x3f803f80,0x3f803f80,0x3f803f80,0x3f803f80,
  0x3f803f80,0x3f803f80,0x3f803f80,0x3f803f80,0x3f803f80,0x3f803f80,0x3f803f80,0x3f803f80,0x3f803f80,0x3f803f80,0x3f803f80,0x3f803f80,
  0x3f803f80,0x3f803f80,0x3f803f80,0x3f803f80,0x3f803f80,0x3f803f80,0x3f803f80,0x3f803f80,0x3f803f80,0x3f803f80,0x3f803f80,0x3f803f80,
  0x3f803f80,0x3f803f80,0x3f803f80,0x3f803f80,0x3f803f80,0x3f803f80,0x3f803f80,0x3f803f80,0x3f803f80,0x3f803f80,0x3f803f80,0x3f803f80,
  0x3f803f80,0x3f803f80,0x3f803f80,0x3f803f80,0x3f803f80,0x3f803f80,0x3f803f80,0x3f803f80,0x3f803f80,0x3f803f80,0x3f803f80,0x3f803f80,
  0x3f803f80,0x3f803f80,0x3f803f80,0x3f803f80,0x3f803f80,0x3f803f80,0x3f803f80,0x3f803f80,0x3f803f80,0x3f803f80,0x3f803f80,0x3f803f80,
  0x3f803f80,0x3f803f80,0x3f803f80,0x3f803f80,0x3f803f80,0x3f803f80,0x3f803f80,0x3f803f80,0x3f803f80,0x3f803f80,0x3f803f80,0x3f803f80,
  0x3f803f80,0x3f803f80,0x3f803f80,0x3f803f80,0x3f803f80,0x3f803f80,0x3f803f80,0x3f803f80,0x3f803f80,0x3f803f80,0x3f803f80,0x3f803f80,
  0x3f803f80,0x3f803f80,0x3f803f80,0x3f803f80,0x3f803f80,0x3f803f80,0x3f803f80,0x3f803f80,0x3f803f80,0x3f803f80,0x3f803f80,0x3f803f80,
  0x3f803f80,0x3f803f80,0x3f803f80,0x3f803f80,0x3f803f80,0x3f803f80,0x3f803f80,0x3f803f80,0x3f803f80,0x3f803f80,0x3f803f80,0x3f803f80,
  0x3f803f80,0x3f803f80,0x3f803f80,0x3f803f80,0x3f803f80,0x3f803f80,0x3f803f80,0x3f803f80,0x3f803f80,0x3f803f80,0x3f803f80,0x3f803f80,
  0x3f803f80,0x3f803f80,0x3f803f80,0x3f803f80,0x3f803f80,0x3f803f80,0x3f803f80,0x3f803f80,0x3f803f80,0x3f803f80,0x3f803f80,0x3f803f80,
  0x3f803f80,0x3f803f80,0x3f803f80,0x3f803f80,0x3f803f80,0x3f803f80,0x3f803f80,0x3f803f80,0x3f803f80,0x3f803f80,0x3f803f80,0x3f803f80,
  0x3f803f80,0x3f803f80,0x3f803f80,0x3f803f80,0x3f803f80,0x3f803f80,0x3f803f80,0x3f803f80,0x3f803f80,0x3f803f80,0x3f803f80,0x3f803f80,
  0x3f803f80,0x3f803f80,0x3f803f80,0x3f803f80,0x3f803f80,0x3f803f80,0x3f803f80,0x3f803f80,0x3f803f80,0x3f803f80,0x3f803f80,0x3f803f80,
  0x3f803f80,0x3f803f80,0x3f803f80,0x3f803f80,0x3f803f80,0x3f803f80,0x3f803f80,0x3f803f80,0x3f803f80,0x3f803f80,0x3f803f80,0x3f803f80,
  0x3f803f80,0x3f803f80,0x3f803f80,0x3f803f80,0x3f803f80,0x3f803f80,0x3f803f80,0x3f803f80,0x3f803f80,0x3f803f80,0x3f803f80,0x3f803f80,
  0x3f803f80,0x3f803f80,0x3f803f80,0x3f803f80,0x3f803f80,0x3f803f80,0x3f803f80,0x3f803f80,0x3f803f80,0x3f803f80,0x3f803f80,0x3f803f80,
  0x3f803f80,0x3f803f80,0x3f803f80,0x3f803f80,0x3f803f80,0x3f803f80,0x3f803f80,0x3f803f80,0x3f803f80,0x3f803f80,0x3f803f80,0x3f803f80,
  0x3f803f80,0x3f803f80,0x3f803f80,0x3f803f80,0x3f803f80,0x3f803f80,0x3f803f80,0x3f803f80,0x3f803f80,0x3f803f80,0x3f803f80,0x3f803f80,
  0x3f803f80,0x3f803f80,0x3f803f80,0x3f803f80,0x3f803f80,0x3f803f80,0x3f803f80,0x3f803f80,0x3f803f80,0x3f803f80,0x3f803f80,0x3f803f80,
  0x3f803f80,0x3f803f80,0x3f803f80,0x3f803f80,0x3f803f80,0x3f803f80,0x3f803f80,0x3f803f80,0x3f803f80,0x3f803f80,0x3f803f80,0x3f803f80,
  0x3f803f80,0x3f803f80,0x3f803f80,0x3f803f80,0x3f803f80,0x3f803f80,0x3f803f80,0x3f803f80,0x3f803f80,0x3f803f80,0x3f803f80,0x3f803f80,
  0x3f803f80,0x3f803f80,0x3f803f80,0x3f803f80,0x3f803f80,0x3f803f80,0x3f803f80,0x3f803f80,0x3f803f80,0x3f803f80,0x3f803f80,0x3f803f80,
  0x3f803f80,0x3f803f80,0x3f803f80,0x3f803f80,0x3f803f80,0x3f803f80,0x3f803f80,0x3f803f80,0x3f803f80,0x3f803f80,0x3f803f80,0x3f803f80,
  0x3f803f80,0x3f803f80,0x3f803f80,0x3f803f80,
};

__device__ __align__(128) float    g_part[16][8][2176];
__device__ __align__(128) float    g_kv[16][2176];
constexpr int OBLK = 16 * 1024 + 32;
__device__ __align__(128) uint4    g_o[16 * OBLK];
#define GSTAMP(role, i) do {} while (0)
#define STAMP(role, i) do {} while (0)
#define PDUMP(role) do {} while (0)
#define PROF_SMEM 0

constexpr int STAGE_BYTES = 57344;
constexpr int OFF_H = 4 * 16384, OFF_VP = 9 * 16384, OFF_SPARE = 10 * 16384;
constexpr int OFF_XT = 172032, XT_STRIDE = 4112;
constexpr int OFF_BAR = 204928, OFF_EPOCH = OFF_BAR + 640, OFF_EX = OFF_BAR + 656, OFF_D = OFF_BAR + 672, OFF_SCALE = OFF_BAR + 704;
constexpr int OFF_F2F = 205824, OFF_F2I = 207872, OFF_F4 = 209920, OFF_ONES = 214016, OFF_KVB = 214016;
constexpr int OFF_STG = 219136, STG_STRIDE = 4352, SMEM_TOTAL = 232192 + PROF_SMEM;
enum { B_FULL1 = 0, B_EMPTY1 = 3, B_Q = 6, B_ODONE1 = 7, B_O1RDY = 8, B_H = 9, B_XRAW = 10, B_XT = 11, B_KV = 12, B_Y = 13,  B_AFREE = 15,
       B_STG = 18, B_ODONE = 24, B_XFREE = 25, B_FULL2 = 33, B_CONS2 = 49, B_SFREE = 14, B_KV1 = 61, B_OLOC = 60, B_PKRDY = 62, B_PKFREE = 64, B_H2 = 65, B_G1DONE = 66, B_COUNT = 67, B_FIRST = 67 };
constexpr uint64_t SLOT_A = 0x6859468594685948ull, SLOT_B = 0x7103271032710326ull;
constexpr int NPRE = 6, BEARLY = 3;
__host__ __device__ constexpr int bar_count(int i) {
  return i < B_EMPTY1 ? 1 : i < B_Q ? 4 : i == B_XT ? 4 : i == B_H ? 4 : (i == B_SFREE || i == B_G1DONE) ? 2 : i >= B_PKFREE ? 4 : i >= B_PKRDY ? 8 : i == B_Y ? 9
       : (i >= B_AFREE && i < B_STG) ? 16 : (i == B_ODONE || i == B_ODONE1) ? 8 : (i >= B_XFREE && i < B_FULL2) ? 4
       : i == B_KV1 ? 1 : i == B_OLOC ? 2 : i >= B_CONS2 ? 4 : (i >= B_FULL2 && i < B_FULL2 + NPRE) ? 2 : 1;
}
__host__ __device__ constexpr uint64_t bar_counts(int r) {
  uint64_t v = 0;
  for (int w = 0; w < 11; w++) v |= (uint64_t)(bar_count(1 + 11 * r + w) - 1) << (4 * w);
  return v;
}
constexpr uint32_t SW128 = 64 | (1u << 30);
constexpr int SPIN_LIMIT = 1 << 22;
#define RC 200
#define TAIL3 0
#define PFD 3
#define QPF 6
#define D1 100
#define HSTART 1500
#define PACE 800
#define BPACE 250
#define PD1 700
#define PD2 450
#define OCH 3
#define O1D 0
#define TRICK 3
#define HOLD2 12

__device__ __forceinline__ uint32_t smem_u32(const void* p) { return (uint32_t)__cvta_generic_to_shared(p); }
__device__ __forceinline__ void wg_fence() { asm volatile("wgmma.fence.sync.aligned;" ::: "memory"); }
__device__ __forceinline__ void wg_commit() { asm volatile("wgmma.commit_group.sync.aligned;" ::: "memory"); }
template <int N> __device__ __forceinline__ void wg_wait() { asm volatile("wgmma.wait_group.sync.aligned %0;" ::"n"(N) : "memory"); }
template <int N> __device__ __forceinline__ void keep(float (&d)[N]) {
#pragma unroll
  for (int i = 0; i < N; i++) asm volatile("" : "+f"(d[i])::"memory");
}
__device__ __forceinline__ void mbar_init(uint32_t bar, int cnt) { asm volatile("mbarrier.init.shared::cta.b64 [%0], %1;" ::"r"(bar), "r"(cnt)); }
__device__ __forceinline__ void mbar_expect(uint32_t bar, int bytes) { asm volatile("mbarrier.arrive.expect_tx.shared::cta.b64 _, [%0], %1;" ::"r"(bar), "r"(bytes) : "memory"); }
__device__ __forceinline__ void mbar_arrive(uint32_t bar) { asm volatile("mbarrier.arrive.shared::cta.b64 _, [%0];" ::"r"(bar) : "memory"); }
__device__ __forceinline__ void mbar_arrive_cl(uint32_t bar, uint32_t cta) {
  asm volatile("{\n.reg .b32 r;\nmapa.shared::cluster.u32 r, %0, %1;\nmbarrier.arrive.shared::cluster.b64 _, [r];\n}\n" ::"r"(bar), "r"(cta) : "memory");
}
__device__ __forceinline__ void mbar_wait(uint32_t bar, uint32_t parity) {
  asm volatile("{\n.reg .pred p;\n.reg .u32 n;\nmov.u32 n, 0;\n"
               "W_%=:\nmbarrier.try_wait.parity.shared::cta.b64 p, [%0], %1;\n@p bra D_%=;\n"
               "add.u32 n, n, 1;\nsetp.lt.u32 p, n, %2;\n@p bra W_%=;\ntrap;\nD_%=:\n}\n" ::"r"(bar), "r"(parity), "n"(SPIN_LIMIT) : "memory");
}
__device__ __forceinline__ void fence_async() { asm volatile("fence.proxy.async.shared::cta;" ::: "memory"); }
__device__ __forceinline__ void bar_sync(int id) { asm volatile("bar.sync %0, 128;" ::"r"(id) : "memory"); }
__device__ __forceinline__ void tma2d(uint32_t dst, const CUtensorMap* m, int c0, int c1, uint32_t bar) {
  asm volatile("cp.async.bulk.tensor.2d.shared::cluster.global.mbarrier::complete_tx::bytes [%0], [%1, {%3, %4}], [%2];"
               ::"r"(dst), "l"(m), "r"(bar), "r"(c0), "r"(c1) : "memory");
}
__device__ __forceinline__ void tma2d_mc(uint32_t dst, const CUtensorMap* m, int c0, int c1, uint32_t bar) {
  asm volatile("cp.async.bulk.tensor.2d.shared::cluster.global.mbarrier::complete_tx::bytes.multicast::cluster [%0], [%1, {%3, %4}], [%2], %5;"
               ::"r"(dst), "l"(m), "r"(bar), "r"(c0), "r"(c1), "h"((uint16_t)3) : "memory");
}
__device__ __forceinline__ void tma3d(uint32_t dst, const CUtensorMap* m, int c0, int c1, int c2, uint32_t bar) {
  asm volatile("cp.async.bulk.tensor.3d.shared::cluster.global.mbarrier::complete_tx::bytes [%0], [%1, {%3, %4, %5}], [%2];"
               ::"r"(dst), "l"(m), "r"(bar), "r"(c0), "r"(c1), "r"(c2) : "memory");
}
__device__ __forceinline__ void tma4d(uint32_t dst, const CUtensorMap* m, int c0, int c1, int c2, int c3, uint32_t bar) {
  asm volatile("cp.async.bulk.tensor.4d.shared::cluster.global.mbarrier::complete_tx::bytes [%0], [%1, {%3, %4, %5, %6}], [%2];"
               ::"r"(dst), "l"(m), "r"(bar), "r"(c0), "r"(c1), "r"(c2), "r"(c3) : "memory");
}
__device__ __forceinline__ void bulk_ld(uint32_t dst, const void* src, int bytes, uint32_t bar) {
  asm volatile("cp.async.bulk.shared::cluster.global.mbarrier::complete_tx::bytes [%0], [%1], %2, [%3];" ::"r"(dst), "l"(src), "r"(bytes), "r"(bar) : "memory");
}
__device__ __forceinline__ void bulk_ld_mc(uint32_t dst, const void* src, int bytes, uint32_t bar) {
  asm volatile("cp.async.bulk.shared::cluster.global.mbarrier::complete_tx::bytes.multicast::cluster [%0], [%1], %2, [%3], %4;"
               ::"r"(dst), "l"(src), "r"(bytes), "r"(bar), "h"((uint16_t)3) : "memory");
}
__device__ __forceinline__ void tma2d_st(const CUtensorMap* m, uint32_t src, int c0, int c1) {
  asm volatile("cp.async.bulk.tensor.2d.global.shared::cta.bulk_group [%0, {%2, %3}], [%1];" ::"l"(m), "r"(src), "r"(c0), "r"(c1) : "memory");
}
__device__ __forceinline__ void ldsm4(uint32_t (&r)[4], uint32_t a) {
  asm volatile("ldmatrix.sync.aligned.m8n8.x4.shared.b16 {%0,%1,%2,%3}, [%4];" : "=r"(r[0]), "=r"(r[1]), "=r"(r[2]), "=r"(r[3]) : "r"(a) : "memory");
}
__device__ __forceinline__ void ldsm4t(uint32_t (&r)[4], uint32_t a) {
  asm volatile("ldmatrix.sync.aligned.m8n8.x4.trans.shared.b16 {%0,%1,%2,%3}, [%4];" : "=r"(r[0]), "=r"(r[1]), "=r"(r[2]), "=r"(r[3]) : "r"(a) : "memory");
}
__device__ __forceinline__ void stsm4(uint32_t a, uint32_t r0, uint32_t r1, uint32_t r2, uint32_t r3) {
  asm volatile("stmatrix.sync.aligned.m8n8.x4.shared.b16 [%0], {%1,%2,%3,%4};" ::"r"(a), "r"(r0), "r"(r1), "r"(r2), "r"(r3) : "memory");
}
__device__ __forceinline__ uint32_t pk2(float lo, float hi) { uint32_t r; asm("cvt.rn.bf16x2.f32 %0, %1, %2;" : "=r"(r) : "f"(hi), "f"(lo)); return r; }
__device__ __forceinline__ uint32_t hmul(uint32_t a, uint32_t b) { uint32_t r; asm("mul.rn.bf16x2 %0, %1, %2;" : "=r"(r) : "r"(a), "r"(b)); return r; }
__device__ __forceinline__ uint32_t hadd(uint32_t a, uint32_t b) { uint32_t r; asm("add.rn.bf16x2 %0, %1, %2;" : "=r"(r) : "r"(a), "r"(b)); return r; }
__device__ __forceinline__ uint32_t hmaxabs(uint32_t a, uint32_t b) { uint32_t r; asm("max.xorsign.abs.bf16x2 %0, %1, %2;" : "=r"(r) : "r"(a), "r"(b)); return r; }
__device__ __forceinline__ float ex2(float x) { float r; asm("ex2.approx.ftz.f32 %0, %1;" : "=f"(r) : "f"(x)); return r; }
__device__ __forceinline__ float rcp_fast(float x) { float r; asm("rcp.approx.ftz.f32 %0, %1;" : "=f"(r) : "f"(x)); return r; }
__device__ __forceinline__ uint32_t phi2(float lo, float hi) {
  const float c = 1.4426950408889634f;
  uint32_t r;
  asm("max.bf16x2 %0, %1, %2;" : "=r"(r) : "r"(pk2(lo, hi)), "r"(hadd(pk2(ex2(-fabsf(fmaf(lo, c, -c))), ex2(-fabsf(fmaf(hi, c, -c)))), 0x35863586u)));
  return r;
}
__device__ __forceinline__ uint32_t opaque_one() { uint32_t v; asm volatile("mov.u32 %0, %%nctaid.y;" : "=r"(v)); return v; }
__device__ __forceinline__ bool opaque_true() { uint32_t v; asm volatile("mov.u32 %0, %%nctaid.y;" : "=r"(v)); return v != 0; }
__device__ __forceinline__ int norm_exp(uint32_t (&v)[32], float f0) {
  uint32_t m[4] = {hmaxabs(__float_as_uint(f0) >> 16, v[0]), v[1], v[2], v[3]};
#pragma unroll
  for (int i = 4; i < 32; i++) m[i & 3] = hmaxabs(m[i & 3], v[i]);
  m[0] = hmaxabs(hmaxabs(m[0], m[1]), hmaxabs(m[2], m[3]));
  const int e = min(max((int)(__reduce_max_sync(~0u, max(m[0] & 0x7FFFu, (m[0] >> 16) & 0x7FFFu)) >> 7), 1), 253);
  if (e > 141) {
#pragma unroll
    for (int i = 0; i < 32; i++) v[i] = hmul(v[i], 0x07000700u);
  }
  return e;
}
__device__ __forceinline__ void norm_cvt(uint32_t (&v)[32], float f0, int e) {
  const uint32_t sc = (e > 141 ? 255 - e : 142 - e) * 0x00800080u;
#pragma unroll
  for (int i = 0; i < 32; i++) {
    const uint32_t a = hmul(v[i], sc);
    v[i] = (a & 0x0FFF0FFFu) * 7 + a;
  }
  v[0] = __byte_perm(v[0], __half_as_ushort(__float2half_rn(f0 * __uint_as_float((254 - e) << 23))), 0x3254);
}
__device__ __forceinline__ void poll_ge(const unsigned* p, unsigned target) {
#pragma unroll 1
  for (int n = 0; n < SPIN_LIMIT; n++) {
    unsigned v;
    asm volatile("ld.relaxed.gpu.global.u32 %0, [%1];" : "=r"(v) : "l"(p) : "memory");
    if (__all_sync(~0u, (int)(v - target) >= 0)) { asm volatile("fence.acquire.gpu;" ::: "memory"); return; }
  }
  __trap();
}

__device__ __forceinline__ bool elect_one() {
  uint32_t p;
  asm volatile("{\n.reg .pred p;\nelect.sync _|p, 0xffffffff;\nselp.u32 %0, 1, 0, p;\n}\n" : "=r"(p));
  return p;
}
__device__ __forceinline__ uint4 ld_na4(const void* p) {
  uint4 v;
  asm volatile("ld.global.L1::no_allocate.v4.u32 {%0,%1,%2,%3}, [%4];" : "=r"(v.x), "=r"(v.y), "=r"(v.z), "=r"(v.w) : "l"(p) : "memory");
  return v;
}
__device__ __forceinline__ void st_cg4(void* p, uint4 v) {
  asm volatile("st.global.cg.v4.u32 [%0], {%1,%2,%3,%4};" ::"l"(p), "r"(v.x), "r"(v.y), "r"(v.z), "r"(v.w) : "memory");
}
__device__ __forceinline__ uint32_t mapa(uint32_t a, uint32_t cta) { uint32_t r; asm("mapa.shared::cluster.u32 %0, %1, %2;" : "=r"(r) : "r"(a), "r"(cta)); return r; }
__device__ __forceinline__ void st_async(uint32_t a, uint32_t v, uint32_t bar) {
  asm volatile("st.async.weak.shared::cluster.mbarrier::complete_tx::bytes.b32 [%0], %1, [%2];" ::"r"(a), "r"(v), "r"(bar) : "memory");
}
__device__ __forceinline__ void st_async4(uint32_t a, uint32_t x, uint32_t y, uint32_t z, uint32_t w, uint32_t bar) {
  asm volatile("st.async.weak.shared::cluster.mbarrier::complete_tx::bytes.v4.b32 [%0], {%1,%2,%3,%4}, [%5];" ::"r"(a), "r"(x), "r"(y), "r"(z), "r"(w), "r"(bar) : "memory");
}
__device__ __forceinline__ void tma_q_ld(uint32_t dst, const CUtensorMap* m, int ch, int quarter, int g0, uint32_t bar) {
  asm volatile("cp.async.bulk.tensor.5d.shared::cluster.global.mbarrier::complete_tx::bytes [%0], [%1, {%3, %6, %6, %4, %5}], [%2];"
               ::"r"(dst), "l"(m), "r"(bar), "r"(ch), "r"(8 * quarter), "r"(g0), "r"(0) : "memory");
}
__device__ __forceinline__ void tma_q_st(const CUtensorMap* m, uint32_t src, int ch, int quarter, int g0) {
  asm volatile("cp.async.bulk.tensor.5d.global.shared::cta.bulk_group [%0, {%2, %5, %5, %3, %4}], [%1];"
               ::"l"(m), "r"(src), "r"(ch), "r"(8 * quarter), "r"(g0), "r"(0) : "memory");
}
__device__ __forceinline__ uint4 ld_rlx4(const void* p) {
  uint4 v;
  asm volatile("{\n.reg .b128 t;\n.reg .b64 a, b;\nld.relaxed.gpu.global.b128 t, [%4];\nmov.b128 {a, b}, t;\nmov.b64 {%0, %1}, a;\nmov.b64 {%2, %3}, b;\n}\n"
               : "=r"(v.x), "=r"(v.y), "=r"(v.z), "=r"(v.w) : "l"(p) : "memory");
  return v;
}
__device__ __forceinline__ void ld_stale4(uint4& v, const void* p, uint32_t tag) {
  asm volatile("{\n.reg .b128 t;\n.reg .b64 a, b;\n.reg .b32 x;\n.reg .pred p;\n"
               "lop3.b32 x, %0, %5, 1, 0x28;\nsetp.ne.u32 p, x, 0;\n"
               "mov.b64 a, {%0, %1};\nmov.b64 b, {%2, %3};\nmov.b128 t, {a, b};\n"
               "@p ld.relaxed.gpu.global.b128 t, [%4];\n"
               "mov.b128 {a, b}, t;\nmov.b64 {%0, %1}, a;\nmov.b64 {%2, %3}, b;\n}\n"
               : "+r"(v.x), "+r"(v.y), "+r"(v.z), "+r"(v.w) : "l"(p), "r"(tag) : "memory");
}
__device__ __forceinline__ void st_tag4(void* p, float a, float b, float c, float d, uint32_t tag) {
  asm volatile("{\n.reg .b128 t;\n.reg .b64 a, b;\nmov.b64 a, {%1, %2};\nmov.b64 b, {%3, %4};\nmov.b128 t, {a, b};\nst.relaxed.gpu.global.b128 [%0], t;\n}\n"
               ::"l"(p), "r"((__float_as_uint(a) & ~1u) | tag), "f"(b), "f"(c), "f"(d) : "memory");
}
__device__ __forceinline__ uint32_t stale8(const uint4 (&f)[8], uint32_t tag) {
  uint32_t r[4];
#pragma unroll
  for (int i = 0; i < 4; i++) asm("lop3.b32 %0, %1, %2, %3, 0x7E;" : "=r"(r[i]) : "r"(f[2 * i].x), "r"(f[2 * i + 1].x), "r"(tag));
  asm("lop3.b32 %0, %0, %1, %2, 0xFE;" : "+r"(r[0]) : "r"(r[1]), "r"(r[2]));
  return r[0] | r[3];
}

struct ConvC { uint32_t a1[2][4], wa[2], wb[2], sg; };
__device__ __forceinline__ uint64_t dsc(uint32_t lo, uint32_t hi) { return ((uint64_t)hi << 32) | lo; }
__device__ __forceinline__ uint32_t hfma(uint32_t a, uint32_t b, uint32_t c) { uint32_t r; asm("fma.rn.f16x2 %0, %1, %2, %3;" : "=r"(r) : "r"(a), "r"(b), "r"(c)); return r; }
__device__ __forceinline__ uint32_t hfnma(uint32_t a, uint32_t b, uint32_t c) { uint32_t r; asm("{.reg .b32 n; neg.f16x2 n, %1; fma.rn.f16x2 %0, n, %2, %3;}" : "=r"(r) : "r"(a), "r"(b), "r"(c)); return r; }
__device__ __forceinline__ uint32_t hmul16(uint32_t a, uint32_t b) { uint32_t r; asm("mul.rn.f16x2 %0, %1, %2;" : "=r"(r) : "r"(a), "r"(b)); return r; }
template <int N> __device__ __forceinline__ void keepu(uint32_t (&d)[N]) {
#pragma unroll
  for (int i = 0; i < N; i++) asm volatile("" : "+r"(d[i])::"memory");
}
__device__ __forceinline__ void conv_m1(const ConvC& K, uint32_t (&u)[16], uint32_t l) {
  wg_fence();
  wgmma_hrs_n64<1>(u, K.a1[0][0], K.a1[0][1], K.a1[0][2], K.a1[0][3], dsc(l, 32), 0);
  wgmma_hrs_n64<1>(u, K.a1[1][0], K.a1[1][1], K.a1[1][2], K.a1[1][3], dsc(l + 16, 32), 1);
  wg_commit();
}
__device__ __forceinline__ void conv_s2(const ConvC& K, uint32_t (&u)[16], uint32_t (&Z)[2][8], uint32_t dfl) {
  uint32_t fr[8], fi[8];
#pragma unroll
  for (int c = 0; c < 8; c++) {
    const uint32_t r = hfma(K.wa[c & 1], u[2 * c + 1], u[2 * c]);
    fi[c] = hfma(K.wb[c & 1], r, u[2 * c + 1]);
    fr[c] = hfma(K.wa[c & 1], fi[c], r);
  }
  wg_fence();
#pragma unroll
  for (int p = 0; p < 2; p++) {
    wgmma_hrs_n32<0>(Z[p], fr[4 * p], fr[4 * p + 2], fr[4 * p + 1], fr[4 * p + 3], dsc(dfl, 32), 0);
    wgmma_hrs_n32<0>(Z[p], fi[4 * p], fi[4 * p + 2], fi[4 * p + 1], fi[4 * p + 3], dsc(dfl + 16, 32), 1);
  }
  wg_commit();
}
__device__ __forceinline__ void conv_win(const ConvC& K, const uint32_t (&X)[2][8], uint32_t (&W)[2][8]) {
#pragma unroll
  for (int b = 0; b < 4; b++)
#pragma unroll
    for (int c = 0; c < 2; c++) {
      const uint32_t xr = X[b >> 1][2 * c + (b & 1)], xi = X[b >> 1][4 + 2 * c + (b & 1)];
      const int a = b ? b - 1 : 0;
      W[b >> 1][2 * c + (b & 1)] = b ? hfnma(K.sg, X[a >> 1][4 + 2 * c + (a & 1)], xr) : xr;
      W[b >> 1][4 + 2 * c + (b & 1)] = b ? hfma(K.sg, X[a >> 1][2 * c + (a & 1)], xi) : xi;
    }
}
template <int p>
__device__ __forceinline__ void conv_pw(uint32_t (&X)[2][8], uint32_t (&H)[2][8], uint32_t (&V)[8], uint32_t dil) {
  uint32_t pr[2][2], pi[2][2];
#pragma unroll
  for (int jj = 0; jj < 2; jj++)
#pragma unroll
    for (int c = 0; c < 2; c++) {
      const int j = 2 * p + jj;
      uint32_t sr = 0, si = 0;
#pragma unroll
      for (int a = 0; a <= j; a++) {
        const int b = j - a;
        const uint32_t hr = H[a >> 1][2 * c + (a & 1)], hi = H[a >> 1][4 + 2 * c + (a & 1)];
        const uint32_t xr = X[b >> 1][2 * c + (b & 1)], xi = X[b >> 1][4 + 2 * c + (b & 1)];
        sr = a == 0 ? hmul16(hr, xr) : hfma(hr, xr, sr);
        si = a == 0 ? hmul16(hr, xi) : hfma(hr, xi, si);
        sr = hfnma(hi, xi, sr);
        si = hfma(hi, xr, si);
      }
      pr[jj][c] = sr; pi[jj][c] = si;
    }
  wg_fence();
  wgmma_hrs_n32<0>(V, pr[0][0], pr[1][0], pr[0][1], pr[1][1], dsc(dil, 32), 0);
  wgmma_hrs_n32<0>(V, pi[0][0], pi[1][0], pi[0][1], pi[1][1], dsc(dil + 16, 32), 1);
  wg_commit();
}
template <int p>
__device__ __forceinline__ void conv_it(const ConvC& K, uint32_t (&V)[8], uint32_t vst) {
#pragma unroll
  for (int jj = 0; jj < 2; jj++) {
    uint32_t wr[2], wi[2];
#pragma unroll
    for (int c = 0; c < 2; c++) {
      const uint32_t r = hfnma(K.wa[c], V[4 + 2 * c + jj], V[2 * c + jj]);
      wi[c] = hfnma(K.wb[c], r, V[4 + 2 * c + jj]);
      wr[c] = hfnma(K.wa[c], wi[c], r);
    }
    stsm4(vst + (2 * p + jj) * 2048, wr[0], wr[1], wi[0], wi[1]);
  }
}
__device__ __forceinline__ void conv_m4(uint32_t (&y)[8], uint32_t (&a)[4][4], uint32_t d4l) {
  wg_fence();
  wgmma_hrs_n32<0>(y, a[0][0], a[0][1], a[0][2], a[0][3], dsc(d4l, 64), 0);
#pragma unroll
  for (int s = 1; s < 4; s++) wgmma_hrs_n32<0>(y, a[s][0], a[s][1], a[s][2], a[s][3], dsc(d4l + s * 16, 64), 1);
  wg_commit();
}

struct Params {
  CUtensorMap tmX0, tmW, tmX, tmWo, tmWo1, tmK, tmV, tmQ, tmOA, tmOB;
  const __nv_bfloat16 *shift_k, *h, *D, *x, *w, *wo, *q;
  float *part, *kv;
  uint4* o;
  const uint32_t *thr, *img;
};

__global__ void __cluster_dims__(2, 1, 1) __launch_bounds__(384, 1) fused_kernel(const __grid_constant__ Params P) {
  extern __shared__ __align__(1024) uint8_t smem[];
#define MAP_PF(m) asm volatile("prefetch.tensormap [%0];" ::"l"(&P.m) : "memory")
  if (threadIdx.x == 0) { MAP_PF(tmX0); MAP_PF(tmW); MAP_PF(tmX); }
  const uint32_t sb = __shfl_sync(~0u, smem_u32(smem), 0);
  const uint32_t bars = sb + OFF_BAR;
  const int tid = threadIdx.x, lane = tid & 31;
  const int warp = __shfl_sync(~0u, tid >> 5, 0);
  const int rank = blockIdx.x & 1, pc = blockIdx.x >> 1;
  const unsigned c7 = pc + 6, g7 = (c7 * 37) >> 8;
  const int mb = pc < 4 ? 4 + pc : pc < 36 ? (pc - 4) >> 3 : g7 - 2;
  const int hq = pc < 4 ? 0 : pc < 36 ? (pc - 4) & 7 : 1 + c7 - 7 * g7;
  const int cl = 8 * hq + mb;
  const int hp = 2 * hq + rank;
  const int rb = 2 * mb + (hq >> 2), cb = hq & 3;
#define BAR(i) (bars + 8 * (i))
#define OCNT(rb, hh) ((unsigned*)(P.o + (rb) * OBLK + 16 * 1024 + 8 * (hh)))
#define EPOCH (OCNT(rb, 2)[hp & 7])

  if (tid == 0) { STAMP(0, 0); GSTAMP(0, 30); }
  if (warp == 8) {
    if (elect_one()) {
      mbar_init(BAR(B_FIRST), 1);
      asm volatile("fence.mbarrier_init.release.cluster;" ::: "memory");
      mbar_expect(BAR(B_FIRST), STAGE_BYTES - 16384);
      tma2d(sb, &P.tmX0, 0, mb * 256, BAR(B_FIRST));
      tma2d(sb + 16384, &P.tmX0, 0, mb * 256 + 128, BAR(B_FIRST));
      tma3d(sb + 32768, &P.tmW, hp * 64, 0, 0, BAR(B_FIRST));
      mbar_init(BAR(B_FULL1), 1);
      asm volatile("fence.mbarrier_init.release.cluster;" ::: "memory");
    }
    if (lane == 0) STAMP(3, 21);
  } else if (lane == 0) {
    const int wi = warp - (warp > 8);
#pragma unroll
    for (int r = 0; r < 6; r++)
      if (r < 5 || wi < B_COUNT - 56) mbar_init(BAR(1 + 11 * r + wi), ((uint32_t)(bar_counts(r) >> (4 * wi)) & 15) + 1);
    asm volatile("fence.mbarrier_init.release.cluster;" ::: "memory");
  }
  if (tid == 0) STAMP(2, 6);
  asm volatile("barrier.cluster.arrive.relaxed.aligned;\nbarrier.cluster.wait.aligned;" ::: "memory");
  if (warp == 8 && elect_one()) {
    mbar_expect(BAR(B_FULL1), 16384);
    tma2d_mc(sb + 8192 + rank * 16384, &P.tmX0, 0, mb * 256 + 64 + rank * 128, BAR(B_FULL1));
  }
  if (tid == 256) STAMP(2, 7);

  if (warp < 8) {
    asm volatile("setmaxnreg.inc.sync.aligned.u32 224;");
    const int wg = warp >> 2, w = warp & 3, g = lane >> 2, q = lane & 3, t = tid & 127;
    const bool elect = (t == 0);
    const uint32_t s16 = (sb & 0x3FFFF) >> 4;
    uint32_t pq[2][16], ux[16], uh[16], X[4][2][8], H[4][2][8];
    ConvC K;
    const uint32_t dfl = s16 + (OFF_F2F >> 4) + (8 << 16), dil = s16 + (OFF_F2I >> 4) + (8 << 16), d4l = s16 + (OFF_F4 >> 4) + (8 << 16);
    const uint32_t xl = s16 + (OFF_XT >> 4) + 4 * wg * (XT_STRIDE >> 4) + (8 << 16);
    const uint32_t hl = s16 + (OFF_H >> 4) + wg * 512 + (8 << 16);
    {
      float acc[2][96];
      {
#pragma unroll
        for (int i = 0; i < 192; i++) { acc[i / 96][i % 96] = i % 96 < 64 ? 1.f : 0.f; asm volatile("" : "+f"(acc[i / 96][i % 96])); }
      }
      {
#pragma unroll
        for (int mt = 0; mt < 2; mt++) {
          mbar_wait(BAR(mt ? B_FULL1 : B_FIRST), 0);
          if (mt == 0 && elect) { STAMP(wg, 1); GSTAMP(wg, 26); }
          wg_fence();
#pragma unroll
          for (int ks = 0; ks < 4; ks++)
            wgmma_ss_n192<0, 1>(acc[mt], dsc(s16 + wg * 1024 + mt * 512 + (1 << 16) + ks * 2, SW128), dsc(s16 + 2048 + (512 << 16) + ks * 128, SW128), 1);
        }
        wg_commit();
      }
      int st = 1, ph = 0;
#pragma unroll 1
      for (int kb = 1; kb < (TAIL3 ? 13 : 14); kb++) {
        mbar_wait(BAR(B_FULL1 + st), ph);
        if (kb == 8 && elect) { STAMP(wg, 16); GSTAMP(wg, 25); }
        const uint32_t da = s16 + st * (STAGE_BYTES >> 4) + wg * 1024 + (1 << 16);
        const uint32_t db = s16 + st * (STAGE_BYTES >> 4) + 2048 + (512 << 16);
        wg_fence();
#pragma unroll
        for (int ks = 0; ks < 4; ks++) {
          wgmma_ss_n192<0, 1>(acc[0], dsc(da + ks * 2, SW128), dsc(db + ks * 128, SW128), 1);
          wgmma_ss_n192<0, 1>(acc[1], dsc(da + 512 + ks * 2, SW128), dsc(db + ks * 128, SW128), 1);
        }
        wg_commit();
        wg_wait<1>();
        if (t < 2) mbar_arrive_cl(BAR(B_EMPTY1 + (st == 0 ? 2 : st - 1)), t);
        if (++st == 3) { st = 0; ph ^= 1; }
      }
      const uint32_t s16_ = s16;
#define TAIL_MMA(mt, stage) do { const uint32_t s16 = TAIL3 ? s16_ + opaque_one() - 1 : s16_; wg_fence(); _Pragma("unroll") for (int ks = 0; ks < 4; ks++) \
        wgmma_ss_n192<0, 1>(acc[mt], dsc(s16 + (stage) * (STAGE_BYTES >> 4) + wg * 1024 + (mt) * 512 + (1 << 16) + ks * 2, SW128), \
                            dsc(s16 + (stage) * (STAGE_BYTES >> 4) + 2048 + (512 << 16) + ks * 128, SW128), 1); wg_commit(); } while (0)
      if (TAIL3) {
        mbar_wait(BAR(B_FULL1 + 1), 0);
        TAIL_MMA(0, 1);
        wg_wait<1>();
        if (t < 2) mbar_arrive_cl(BAR(B_EMPTY1 + 0), t);
      }
      mbar_wait(BAR(B_FULL1 + 2), 0);
      TAIL_MMA(0, 2);
      if (!TAIL3) {
        wg_wait<1>();
        if (elect) mbar_arrive(BAR(B_SFREE));
      }
      mbar_wait(BAR(B_FULL1 + 0), 1);
      TAIL_MMA(0, 0);
      if (TAIL3) TAIL_MMA(1, 1); else TAIL_MMA(1, 2);
      const uint32_t lrow = sb + wg * 16384 + (16 * w + 8 * ((lane >> 3) & 1) + (lane & 7)) * 128 + (((lane >> 4) ^ (lane & 7)) << 4);
#define E1K(mt, i) do { if (opaque_true()) { _Pragma("unroll") for (int j = (i); j < (i) + 2; j++) { \
          const float* a = &acc[mt][32 + 8 * j]; const float* b = a + 32; const uint32_t o = (lrow ^ (j * 32)) + (mt) * 8192; \
          stsm4(o + 2 * STAGE_BYTES, pk2(b[0], b[1]), pk2(b[2], b[3]), pk2(b[4], b[5]), pk2(b[6], b[7])); \
          stsm4(o, phi2(a[0], a[1]), phi2(a[2], a[3]), phi2(a[4], a[5]), phi2(a[6], a[7])); } } } while (0)
#define E1Q(mt) do { if (opaque_true()) { _Pragma("unroll") for (int i = 0; i < 16; i++) pq[mt][i] = phi2(acc[mt][2 * i], acc[mt][2 * i + 1]); } } while (0)
#define E1QP(i0, i1) do { if (opaque_true()) { _Pragma("unroll") for (int i = (i0); i < (i1); i++) pq[0][i] = phi2(acc[0][2 * i], acc[0][2 * i + 1]); } } while (0)
#define LOAD_K() do { const uint4* ct = (const uint4*)P.thr + t; \
        _Pragma("unroll") for (int s = 0; s < 2; s++) { const uint4 u = ld_na4(ct + s * 128); K.a1[s][0] = u.x; K.a1[s][1] = u.y; K.a1[s][2] = u.z; K.a1[s][3] = u.w; } \
        const uint4 u = ld_na4(ct + 2 * 128); K.wa[0] = u.x; K.wa[1] = u.y; K.wb[0] = u.z; K.wb[1] = u.w; \
        K.sg = (lane & 4) ? 0xBC00BC00u : 0x3C003C00u; } while (0)
#define PK_READY(mt) do { fence_async(); __syncwarp(); if (lane == 0) mbar_arrive(BAR(B_PKRDY + (mt))); } while (0)
      wg_wait<1>();
      keep(acc[0]);
      if (elect) STAMP(wg, 18);
      E1K(0, 0);
      if (TAIL3) {
        TAIL_MMA(1, 2);
        wg_wait<1>();
        if (elect) mbar_arrive(BAR(B_SFREE));
      } else TAIL_MMA(1, 0);
      E1K(0, 2);
      if (elect) STAMP(wg, 19);
      if (TAIL3) TAIL_MMA(1, 0);
      if (TAIL3) E1QP(0, TAIL3);
      PK_READY(0);
      wg_wait<0>();
      keep(acc[1]);
      if (elect) mbar_arrive(BAR(B_G1DONE));
      asm volatile("setmaxnreg.dec.sync.aligned.u32 %0;" ::"n"(RC));
      if (elect) { STAMP(wg, 2); GSTAMP(wg, 27); }
      E1K(1, 0);
      if (elect) STAMP(wg, 20);
      E1K(1, 2);
      if (elect) STAMP(wg, 21);
      PK_READY(1);
      if (elect) STAMP(wg, 3);
      LOAD_K();
      if (elect) STAMP(wg, 4);
      if (TAIL3 < 16) E1QP(TAIL3, 16);
      E1Q(1);
      if (elect) STAMP(wg, 17);
      mbar_wait(BAR(B_H), 0);
      conv_m1(K, ux, xl);
      conv_m1(K, uh, hl);
      wg_wait<1>(); keepu(ux);
      if (lane == 0) mbar_arrive_cl(BAR(B_XFREE + 4 * wg), rank ^ 1);
      conv_s2(K, ux, X[0], dfl);
      wg_wait<1>(); keepu(uh);
      conv_s2(K, uh, H[0], dfl);
    }
    if (elect) STAMP(wg, 5);
    float acc[64];
#define G2_MMA(da, db, first) do { wg_fence(); _Pragma("unroll") for (int ks = 0; ks < 4; ks++) \
        wgmma_ss_n128<0, 1>(acc, dsc((da) + ks * 2, SW128), dsc((db) + ks * 128, SW128), ks || !(first)); wg_commit(); } while (0)
    const uint32_t a0 = s16 + wg * 512 + (1 << 16), b0 = s16 + (512 << 16);
    uint32_t cons = mapa(BAR(B_CONS2), t & 1);
    const bool rel = __shfl_sync(~0u, t, lane) < 2;
    {
      uint32_t vst = sb + wg * 8192 + w * 512 + lane * 16, vld = sb + wg * 8192 + w * 2048 + lane * 16;
      uint32_t ya = mapa(sb + OFF_XT + 4 * wg * XT_STRIDE + (2 * rank + (w & 1)) * 1024 + lane * 16, w >> 1);
      const uint32_t ybar = mapa(BAR(B_Y), w >> 1);
      asm volatile("" : "+r"(vst), "+r"(vld), "+r"(ya));
      uint32_t W[2][8], V0[8], V1[8], y[8], a[4][4];
      uint4 ov[4];
      uint4* const ot = P.o + (2 * mb + wg) * OBLK + hq * 1024 + (16 * w + g) * 8 + ((4 * rank + q) ^ g);
#define YOUT(i) do { if ((w >> 1) == rank) { \
          asm volatile("st.shared.v4.b32 [%0], {%1,%2,%3,%4};" ::"r"(ya + (i) * XT_STRIDE), "r"(y[0]), "r"(y[1]), "r"(y[2]), "r"(y[3]) : "memory"); \
          asm volatile("st.shared.v4.b32 [%0], {%1,%2,%3,%4};" ::"r"(ya + (i) * XT_STRIDE + 512), "r"(y[4]), "r"(y[5]), "r"(y[6]), "r"(y[7]) : "memory"); \
        } else { \
          mbar_wait(BAR(B_XFREE + 4 * wg + (i)), 0); \
          st_async4(ya + (i) * XT_STRIDE, y[0], y[1], y[2], y[3], ybar); \
          st_async4(ya + (i) * XT_STRIDE + 512, y[4], y[5], y[6], y[7], ybar); } } while (0)
      auto ocalc = [&](const int hh) {
        if (hh == 0) {
          if (elect) STAMP(wg, 8);
          mbar_wait(BAR(B_KV), 0);
          if (elect) STAMP(wg, 9);
        } else mbar_wait(BAR(B_KV1), 0);
        float oa[2][20];
        wg_fence();
#pragma unroll
        for (int m = 0; m < 4; m++) {
          const uint32_t* p = &pq[m & 1][8 * hh + 4 * (m >> 1)];
          wgmma_rs_n40<1>(oa[m & 1], p[0], p[1], p[2], p[3], dsc(s16 + (OFF_KVB >> 4) + hh * 160 + (m >> 1) * 16 + (8 << 16), 32), m >> 1);
        }
        wg_commit();
        wg_wait<0>();
#pragma unroll
        for (int mt = 0; mt < 2; mt++) {
          float (&o)[20] = oa[mt];
          keep(o);
          const uint32_t den = hadd(pk2(o[16], o[18]), 0x35863586u);
#pragma unroll
          for (int r = 0; r < 2; r++) {
            const float ri = rcp_fast(__uint_as_float(r ? (den & 0xFFFF0000u) : (den << 16)));
            uint4 u;
            u.x = pk2(o[2 * r] * ri, o[2 * r + 1] * ri);
            u.y = pk2(o[4 + 2 * r] * ri, o[5 + 2 * r] * ri);
            u.z = pk2(o[8 + 2 * r] * ri, o[9 + 2 * r] * ri);
            u.w = pk2(o[12 + 2 * r] * ri, o[13 + 2 * r] * ri);
            if (hh == 0) st_cg4(ot + (64 * mt + 8 * r) * 8, u); else ov[2 * mt + r] = u;
          }
        }
        if (hh == 0) {
          __syncwarp();
          if (lane == 0) mbar_arrive(BAR(B_ODONE));
          if (elect) STAMP(wg, 10);
        }
      };
      auto trickle = [&](const int qs) {
        const int m = qs - 2 * (OCH + O1D) - (TRICK - 1);
        if (m >= 0 && m < 4) {
          st_cg4(ot + 8 * 1024 + (64 * (m >> 1) + 8 * (m & 1)) * 8, ov[m]);
          if (m == 3) { __syncwarp(); if (lane == 0) mbar_arrive(BAR(B_ODONE1)); }
        }
      };
#pragma unroll
      for (int i = 0; i < 4; i++) {
        const bool nx = i < 3;
        const int n = nx ? i + 1 : i;
        const uint32_t vo = (i & 1) ? OFF_H + (i >> 1) * 16384 : OFF_VP;
        if (2 * i == OCH) ocalc(0);
        if (2 * i == OCH + O1D) ocalc(1);
        if (nx) {
          conv_m1(K, ux, xl + n * (XT_STRIDE >> 4));
          conv_m1(K, uh, hl + (n >> 1) * 1024 + (n & 1) * 256);
        }
        if (2 * i != OCH && 2 * i != OCH + O1D) { if (nx) { if (i > 0) wg_wait<3>(); else wg_wait<2>(); } else wg_wait<1>(); }
        keepu(X[i][0]); keepu(X[i][1]); keepu(H[i][0]); keepu(H[i][1]);
        conv_win(K, X[i], W);
        trickle(4 * i);
        conv_pw<0>(W, H[i], V0, dil);
        conv_pw<1>(W, H[i], V1, dil);
        trickle(4 * i + 1);
        wg_wait<2>();
        if (i > 0) { keepu(y); YOUT(i - 1); }
        if (2 * i + 1 == OCH) ocalc(0);
        if (2 * i + 1 == OCH + O1D) ocalc(1);
        if (nx) {
          keepu(ux); keepu(uh);
          if (lane == 0) mbar_arrive_cl(BAR(B_XFREE + 4 * wg + n), rank ^ 1);
          conv_s2(K, ux, X[n], dfl);
          wg_wait<1>();
        } else wg_wait<0>();
        keepu(V0); keepu(V1);
        trickle(4 * i + 2);
        if (i == 0) mbar_wait(BAR(B_H2), 0);
        conv_it<0>(K, V0, vst + vo);
        conv_it<1>(K, V1, vst + vo);
        if (i == 3) { mbar_wait(BAR(B_FULL2), 0); G2_MMA(a0 + (SLOT_A & 15) * 1024, b0 + (SLOT_B & 15) * 1024, true); }
        bar_sync(1 + wg);
#pragma unroll
        for (int s = 0; s < 4; s++) ldsm4t(a[s], vld + vo + s * 512);
        if (nx) conv_s2(K, uh, H[n], dfl);
        conv_m4(y, a, d4l);
        trickle(4 * i + 3);
        if (i > 0 && lane < 2) mbar_arrive_cl(BAR(B_AFREE + i - 1), lane);
        if (elect && i < 3) STAMP(wg, i < 2 ? 6 + i : 9 + i);
      }
      wg_wait<0>();
      keepu(y);
      if (rel) asm volatile("mbarrier.arrive.shared::cluster.b64 _, [%0];" ::"r"(cons) : "memory");
      YOUT(3);
      __syncwarp();
      if (lane == 0) mbar_arrive(BAR(B_Y));
      if (elect) STAMP(wg, 12);
    }
    {
      uint64_t ta = SLOT_A >> 4, tb = SLOT_B >> 4;
      uint32_t da = a0 + ((uint32_t)ta & 15) * 1024, db = b0 + ((uint32_t)tb & 15) * 1024, fb = BAR(B_FULL2 + 1);
#pragma unroll 1
      for (int kb = 1; kb < HOLD2; kb++) {
        mbar_wait(fb, 0);
        G2_MMA(da, db, false);
        ta >>= 4; tb >>= 4;
        da = a0 + ((uint32_t)ta & 15) * 1024; db = b0 + ((uint32_t)tb & 15) * 1024; fb += 8;
        asm volatile("" : "+r"(da), "+r"(db));
        wg_wait<1>();
        if (kb > 1 && kb < 12 && rel) asm volatile("mbarrier.arrive.shared::cluster.b64 _, [%0];" ::"r"(cons) : "memory");
        cons += 8;
      }
#pragma unroll
      for (int kb = HOLD2; kb < 16; kb++) {
        if (wg == 1) mbar_wait(BAR(B_FULL2 + kb), 0);
        else if (kb == HOLD2) asm volatile("bar.sync 3, 256;" ::: "memory");
        G2_MMA(a0 + ((SLOT_A >> (4 * kb)) & 15) * 1024, b0 + ((SLOT_B >> (4 * kb)) & 15) * 1024, false);
      }
      if (wg == 1) asm volatile("bar.arrive 3, 256;" ::: "memory");
      const uint32_t stg = sb + wg * 8192 + w * 2048, so0 = ((SLOT_A >> 56) & 15) * 16384, so1 = ((SLOT_A >> 60) & 15) * 16384;
      const uint32_t lrow = stg + (8 * ((lane >> 3) & 1) + (lane & 7)) * 128 + (((lane >> 4) ^ (lane & 7)) << 4);
      const int col = 1024 + 256 * cb + 128 * rank, row = 128 * rb + 64 * wg + 16 * w;
      wg_wait<0>();
      keep(acc);
      if (elect) { STAMP(wg, 14); GSTAMP(wg, 29); }
#pragma unroll
      for (int cp = 0; cp < 8; cp++) {
        const float* a = &acc[8 * cp];
        stsm4((lrow ^ ((cp & 3) * 32)) + (cp >> 2 ? so1 : so0), pk2(a[0], a[1]), pk2(a[2], a[3]), pk2(a[4], a[5]), pk2(a[6], a[7]));
        if ((cp & 3) == 3) {
          fence_async();
          __syncwarp();
          if (elect_one()) tma2d_st(&P.tmOB, stg + (cp >> 2 ? so1 : so0), col + (cp >> 2) * 64, row);
        }
      }
      asm volatile("cp.async.bulk.commit_group;\ncp.async.bulk.wait_group.read 0;" ::: "memory");
      if (elect) {
        STAMP(wg, 15); GSTAMP(wg, 31); PDUMP(wg); if (wg == 0) PDUMP(2);
      }
    }
  } else {
    asm volatile("setmaxnreg.dec.sync.aligned.u32 56;");
    const int hw = warp - 9, g = lane >> 2, q = lane & 3;
#define sbar (bars + 8 * (B_STG - 18) + 16 * warp)
    if (warp == 8) {
      if (D1) __nanosleep(D1);
      int st = 1, pp = 1;
      const uint8_t* pfx = (const uint8_t*)P.x + (mb * 256 + hp * 16 + (lane & 15)) * 2048;
      const uint8_t* pfw = (const uint8_t*)P.w + (mb * 8 + (lane & 7)) * 6144 + (lane >> 3) * 2048 + hp * 128;
#pragma unroll 1
      for (int kb = 1; kb < 16; kb++) {
        if (kb >= 3) mbar_wait(BAR(B_EMPTY1 + st), pp);
        const uint32_t sa = sb + st * STAGE_BYTES;
        if (elect_one()) {
          mbar_expect(BAR(B_FULL1 + st), STAGE_BYTES);
          tma2d_mc(sa + rank * 16384, &P.tmX, kb * 64, mb * 256 + rank * 128, BAR(B_FULL1 + st));
          tma3d(sa + 32768, &P.tmW, hp * 64, kb * 64, 0, BAR(B_FULL1 + st));
        }
        if (kb == 1 && lane == 0) STAMP(2, 24);
        if (PFD && kb >= 2) {
#pragma unroll 1
          for (int j = kb == 2 ? 3 : kb + PFD; j <= kb + PFD && j < 16; j++) {
            if (lane < 16) asm volatile("prefetch.global.L2 [%0];" ::"l"(pfx + j * 128));
            if (lane < 24) asm volatile("prefetch.global.L2 [%0];" ::"l"(pfw + j * (64 * 6144)));
          }
          if (kb >= QPF && kb < QPF + 8) asm volatile("prefetch.global.L2 [%0];" ::"l"((const uint8_t*)P.q + (blockIdx.x * 256 + (kb - QPF) * 16 + (lane & 16) * 8 + (lane & 15)) * 128));
          if (kb >= 4)
            asm volatile("prefetch.global.L2 [%0];" ::"l"(kb < 12 ? (const uint8_t*)P.h + ((2 * cl + rank) * 256 + (kb - 4) * 32 + lane) * 128
                                                                  : (const uint8_t*)P.wo + (blockIdx.x * 128 + (kb - 12) * 32 + lane) * 128));
        }
        if (++st == 3) { st = 0; pp ^= 1; }
      }
      if (elect_one()) { MAP_PF(tmWo); MAP_PF(tmWo1); }
      if (lane == 0) STAMP(2, 1);
    } else {
      {
        const uint32_t clk0 = __shfl_sync(~0u, (uint32_t)clock(), 0), stg = sb + OFF_STG + hw * STG_STRIDE;
        const unsigned epoch = __shfl_sync(~0u, EPOCH, 0);
        const uint32_t tag = ~epoch & 1;
        uint32_t tap[2][4];
#pragma unroll
        for (int cg = 0; cg < 2; cg++) {
          const uint2 u = __ldg((const uint2*)(P.shift_k + (16 * cl + 8 * cg + g) * 4));
          tap[cg][0] = __byte_perm(u.x, 0, 0x1010); tap[cg][1] = __byte_perm(u.x, 0, 0x3232);
          tap[cg][2] = __byte_perm(u.y, 0, 0x1010); tap[cg][3] = __byte_perm(u.y, 0, 0x3232);
        }
        if (hw == 0 && lane < 8) *(float*)(smem + OFF_D + 4 * lane) = __bfloat162float(P.D[16 * cl + 8 * rank + lane]);
        if (hw == 1 && lane < 24) asm volatile("prefetch.global.L2 [%0];" ::"l"(P.thr + (lane + 24 * rank) * 32));
        if (hw == 0 && elect_one()) {
          *(volatile unsigned*)(smem + OFF_EPOCH) = epoch;
          mbar_expect(BAR(B_XRAW), 16384);
          mbar_expect(BAR(B_Y), 16384 + 64);
        }
#pragma unroll 1
        for (int i = hw * 32 + lane; i < 528; i += 96) st_tag4(P.part + (hp * 8 + mb) * 2176 + 4 * i, 0.f, 0.f, 0.f, 0.f, tag ^ 1);
        if (hw < 2 || lane < 2) st_tag4(P.kv + hp * 2176 + (4 * (hw < 2 ? 64 * mb + 32 * hw + lane : 512 + 8 * (mb & 1) + (mb & 6) + lane)), 0.f, 0.f, 0.f, 0.f, tag ^ 1);
        if (lane == 0) STAMP(3, hw);
        const uint32_t xo = sb + OFF_XT + g * XT_STRIDE + rank * 2048 + q * 4;
        const int krow = 8 + (lane & 7) - (lane >> 3);
        const uint32_t ka = stg + krow * 32 + ((krow & 4) << 2), va = stg + 2304 + lane * 32 + ((lane & 4) << 2);
        int ph = 0, b = 0;
#pragma unroll 1
        for (int ci = hw - 3; ci < 16; ci += 3) {
          const uint32_t bo = b ? OFF_F2F - OFF_STG : 0, bn = b ? 0 : OFF_F2F - OFF_STG;
          if (ci + 3 < 16) {
            while (__any_sync(~0u, (uint32_t)clock() - clk0 < HSTART + (ci + 3) * PACE)) __nanosleep(64);
            if (elect_one()) {
              mbar_expect(sbar + 8 * (b ^ 1), 2304 + 2048);
              tma2d(stg + bn, &P.tmK, 16 * cl, 1024 * rank + 64 * (ci + 3) - 8, sbar + 8 * (b ^ 1));
              tma2d(stg + bn + 2304, &P.tmV, 16 * cl, 1024 * rank + 64 * (ci + 3), sbar + 8 * (b ^ 1));
            }
          }
          if (ci >= 0) {
            mbar_wait(sbar + 8 * b, (ph >> b) & 1);
            ph ^= 1 << b;
#pragma unroll 1
            for (int grp = 0; grp < 2; grp++) {
#pragma unroll
              for (int cg = 0; cg < 2; cg++) {
                const uint32_t dst = mapa(xo + (ci >> 3) * 1024 + ((ci & 7) * 4 + 2 * grp) * 16, cg), xbar = mapa(BAR(B_XRAW), cg);
                uint32_t vv[4], kk[4][4];
                ldsm4t(vv, (va ^ (cg * 16)) + bo + grp * 1024);
#pragma unroll
                for (int rg = 0; rg < 4; rg++) ldsm4t(kk[rg], (ka ^ (cg * 16)) + bo + grp * 1024 + rg * 256);
#pragma unroll
                for (int rg = 0; rg < 4; rg++)
                  vv[rg] = hmul(hadd(hadd(hadd(hmul(kk[rg][3], tap[cg][3]), hmul(kk[rg][2], tap[cg][2])), hmul(kk[rg][1], tap[cg][1])), hmul(kk[rg][0], tap[cg][0])), vv[rg]);
                if (cg == rank) {
#pragma unroll
                  for (int rg = 0; rg < 4; rg++) asm volatile("st.shared.b32 [%0], %1;" ::"r"(dst + (rg & 1) * 512 + (rg >> 1) * 16), "r"(vv[rg]) : "memory");
                } else {
#pragma unroll
                  for (int rg = 0; rg < 4; rg++) st_async(dst + (rg & 1) * 512 + (rg >> 1) * 16, vv[rg], xbar);
                }
              }
            }
          }
          b ^= 1;
        }
      }
      if (lane == 0 && hw == 0) STAMP(3, 3);
      asm volatile("bar.sync 4, 96;" ::: "memory");
      if (hw == 0 && elect_one()) { mbar_expect(BAR(B_XT), 10240); bulk_ld(sb + OFF_F2F, P.img, 10240, BAR(B_XT)); }
      mbar_wait(BAR(B_XRAW), 0);
    }
    int e1 = 0;
#pragma unroll 1
    for (int n = hw < 0 ? 3 : 0; n < 4; n++) {
      const bool isH = n >= 3;
      const int c = isH ? (warp & 1) + 2 * (warp & 2) : hw + 3 * n;
      if (c < 8) {
        int ln;
        asm volatile("mov.u32 %0, %%laneid;" : "=r"(ln));
        uint8_t* dst = smem + (isH ? OFF_H + (c & 2) * 8192 + (c >> 2) * 8192 + (c & 1) * 4096 : OFF_XT + c * XT_STRIDE) + ((ln >> 4) * 512 + (ln & 15) * 16);
        const uint8_t* src0 = isH ? (const uint8_t*)P.h + (16 * cl + 8 * rank + c) * 4096 + ((ln & 15) * 32 + (ln & 16)) : dst;
        const uint8_t* src1 = src0 + (isH ? 512 : 256);
        uint32_t v[32];
#pragma unroll
        for (int i = 0; i < 8; i++) {
          const uint4 u = *(const uint4*)(((i & 1) ? src1 : src0) + (i >> 1) * 1024);
          v[4 * i] = u.x; v[4 * i + 1] = u.y; v[4 * i + 2] = u.z; v[4 * i + 3] = u.w;
        }
        if (isH) mbar_wait(BAR(B_XT), 0);
        const float f0 = __uint_as_float(v[0] << 16) + ((isH && ln == 0) ? *(const float*)(smem + OFF_D + 4 * c) : 0.f);
        const int e = norm_exp(v, f0);
        norm_cvt(v, f0, e);
        if (isH) mbar_wait(BAR(B_SFREE), 0);
        else if (ln == 0) smem[OFF_EX + c] = e;
        e1 = e;
#pragma unroll
        for (int i = 0; i < 8; i++)
          *(uint4*)(dst + (i >> 1) * 1024 + (i & 1) * 256) = make_uint4(v[4 * i], v[4 * i + 1], v[4 * i + 2], v[4 * i + 3]);
        if (n < 2 && elect_one()) {
          if (n == 0) mbar_expect(sbar, 4096);
          tma_q_ld(sb + OFF_STG + 2048 * c, &P.tmQ, 16 * cl, 2 * rank, c, sbar);
        }
      }
      if (n >= 2) {
        fence_async();
        __syncwarp();
        if (lane == 0) { mbar_arrive(BAR(isH ? B_H : B_XT)); STAMP(3, (isH ? 17 : 13) + hw); }
      }
    }
#define SLOT(tab, kb) (sb + ((uint32_t)((tab) >> (4 * (kb))) & 15) * 16384)
#define KT(kb) ((kb) == 0 ? hq : (kb) == hq ? 0 : (kb))
#define LOAD_B(kb) tma4d(SLOT(SLOT_B, kb), &P.tmWo, 0, ((kb) >> 3) * 32, 2 * (KT(kb) & 7), 4 * cb + 2 * rank, BAR(B_FULL2 + (kb)))
#define LOAD_A(kb) bulk_ld_mc(SLOT(SLOT_A, kb) + rank * 8192, P.o + rb * OBLK + KT(kb) * 1024 + rank * 512, 8192, BAR(B_FULL2 + (kb)))
    mbar_wait(BAR(B_G1DONE), 0);
    asm volatile("setmaxnreg.inc.sync.aligned.u32 %0;" ::"n"(504 - 2 * RC));
    {
    int tid;
    asm volatile("mov.u32 %0, %%tid.x;" : "=r"(tid));
    const int lane = tid & 31, g = lane >> 2, q = lane & 3;
    const unsigned epoch = *(volatile unsigned*)(smem + OFF_EPOCH);
    const uint32_t tag = ~epoch & 1;
    const int pi = hw < 2 ? 64 * mb - 288 + tid : 512 + 8 * (mb & 1) + (mb & 6) + (lane & 1);
    const float* psrc = P.part + hp * 8 * 2176 + 4 * pi;
    uint4 f[8];
    {
      const uint32_t s16 = (sb & 0x3FFFF) >> 4;
      const int t = tid & 127, c = 2 + (warp & 1) + 2 * (warp & 2);
      const uint4* hp4 = (const uint4*)(P.h + (16 * cl + 8 * rank + c) * 2048) + ((lane & 15) * 2 + (lane >> 4));
      uint32_t v[32];
#pragma unroll
      for (int i = 0; i < 8; i++) { const uint4 u = ld_na4(hp4 + i * 32); v[4 * i] = u.x; v[4 * i + 1] = u.y; v[4 * i + 2] = u.z; v[4 * i + 3] = u.w; }
      float kva[36];
#pragma unroll
      for (int mt = 0; mt < 2; mt++) {
        mbar_wait(BAR(B_PKRDY + mt), 0);
        wg_fence();
#pragma unroll
        for (int ks = 0; ks < 8; ks++) {
          const uint32_t o = (ks >> 2) * 1024 + mt * 512 + (ks & 3) * 128, vb = (2 * STAGE_BYTES >> 4) + o;
          wgmma_ss_n72<1, 1>(kva, dsc(s16 + o + (1 << 16), SW128), dsc(s16 + vb + (((OFF_ONES >> 4) - vb) << 16), SW128), (mt | ks) != 0);
        }
        wg_commit();
        if (mt == 0 && hw < 0) {
          if (elect_one()) {
#pragma unroll
            for (int kb = 0; kb < BEARLY; kb++) { mbar_expect(BAR(B_FULL2 + kb), 16384); LOAD_B(kb); }
          }
        }
      }
      float* pdst = P.part + (hp * 8 + mb) * 2176 + t * 4;
      float* zdst = P.part + (hp * 8 + mb) * 2176 + 2048 + (t >> 1);
      asm volatile("" : "+l"(pdst), "+l"(zdst));
      wg_wait<0>();
      keep(kva);
      if (hw < 1) {
#pragma unroll
        for (int c = 0; c < 4; c++) st_tag4(pdst + c * 512, kva[4 * c], kva[4 * c + 1], kva[4 * c + 2], kva[4 * c + 3], tag);
      } else {
#pragma unroll
        for (int c = 4; c < 8; c++) st_tag4(pdst + (c - 4) * 512, kva[4 * c], kva[4 * c + 1], kva[4 * c + 2], kva[4 * c + 3], tag);
      }
      const float z2 = __shfl_down_sync(~0u, kva[32], 4), z3 = __shfl_down_sync(~0u, kva[34], 4);
      if (!(lane & 7)) st_tag4(zdst, kva[32], kva[34], z2, z3, tag);
      if (lane == 0) mbar_arrive(BAR(B_PKFREE));
      const uint32_t cst = clock();
      if (hw == 0 && lane == 0) STAMP(3, 24);
      const float f0 = __uint_as_float(v[0] << 16) + (lane == 0 ? *(const float*)(smem + OFF_D + 4 * c) : 0.f);
      const int e = norm_exp(v, f0);
      norm_cvt(v, f0, e);
      if (hw >= 0) {
        while (__any_sync(~0u, (uint32_t)clock() - cst < PD1)) __nanosleep(20);
        if (hw == 0 && lane == 0) STAMP(3, 20);
#pragma unroll
        for (int p = 0; p < 8; p++) f[p] = ld_rlx4(psrc + p * 2176);
      }
      uint8_t* dst = smem + OFF_H + 16384 + (warp & 3) * 4096 + (lane >> 4) * 512 + (lane & 15) * 16;
#pragma unroll
      for (int i = 0; i < 8; i++)
        *(uint4*)(dst + (i >> 1) * 1024 + (i & 1) * 256) = make_uint4(v[4 * i], v[4 * i + 1], v[4 * i + 2], v[4 * i + 3]);
      if (lane < 4) {
        const int cc = c - (lane & 2);
        st_async(mapa(sb + OFF_SCALE + (8 * rank + cc) * 4, lane & 1), min(max(((lane & 2) ? e1 : e) + smem[OFF_EX + cc] - 124, 1), 254) << 23, mapa(BAR(B_Y), lane & 1));
      }
    }
#define H2_READY() do { fence_async(); __syncwarp(); if (lane == 0) mbar_arrive(BAR(B_H2)); } while (0)
    if (warp == 8) {
      H2_READY();
      mbar_wait(BAR(B_PKFREE), 0);
      {
        const uint32_t c0 = clock();
#pragma unroll 1
        for (int i = 0; i < 2 * NPRE - 2 * BEARLY; i++) {
          const int kb = (i >> 1) + BEARLY;
          while (__any_sync(~0u, (uint32_t)clock() - c0 < i * BPACE)) __nanosleep(32);
          if (elect_one()) {
            if (!(i & 1)) mbar_expect(BAR(B_FULL2 + kb), 16384);
            tma4d(SLOT(SLOT_B, kb) + (i & 1) * 8192, &P.tmWo1, 0, 0, 2 * KT(kb), 4 * cb + 2 * rank + (i & 1), BAR(B_FULL2 + kb));
            if (i == 0) mbar_expect(BAR(B_Q), 8192);
            if (i < 4) tma_q_ld(sb + OFF_SPARE + 2048 * i, &P.tmQ, 16 * cl, 2 * rank + (i >> 1), (i + 6) & 7, BAR(B_Q));
          }
        }
      }
      if (elect_one()) { MAP_PF(tmOA); MAP_PF(tmOB); }
      if (lane == 0) STAMP(2, 2);
      {
        if (elect_one()) mbar_expect(BAR(B_FULL2), 16384);
        mbar_wait(BAR(B_OLOC), 0);
        asm volatile("fence.acquire.cluster;\nfence.proxy.async.global;" ::: "memory");
        if (elect_one()) LOAD_A(0);
      }
      mbar_wait(BAR(B_AFREE), 0);
      if (elect_one()) mbar_expect(BAR(B_FULL2 + 1), 16384);
      {
        const uint32_t dst = SLOT(SLOT_A, 1) + rank * 8192;
        const uint4* src = P.o + rb * OBLK + KT(1) * 1024 + rank * 512;
        poll_ge(OCNT(rb, 0), 16 * (epoch + 1));
        asm volatile("fence.proxy.async.global;" ::: "memory");
        if (lane == 0) STAMP(2, 3);
        if (elect_one()) bulk_ld_mc(dst, src, 8192, BAR(B_FULL2 + 1));
        if (lane == 0) STAMP(3, 23);
      }
#pragma unroll 1
      for (int kb = 2; kb < NPRE; kb++) {
        mbar_wait(BAR(kb < 4 ? B_AFREE + kb - 1 : B_CONS2), 0);
        if (elect_one()) { mbar_expect(BAR(B_FULL2 + kb), 16384); LOAD_A(kb); }
      }
#pragma unroll 1
      for (int kb = NPRE; kb < 16; kb++) {
        mbar_wait(BAR(B_CONS2 + kb - 5), 0);
        if (kb == 8) mbar_wait(BAR(B_O1RDY), 0);
        if (elect_one()) { mbar_expect(BAR(B_FULL2 + kb), 32768); LOAD_A(kb); LOAD_B(kb); }
      }
      if (lane == 0) { EPOCH = epoch + 1; STAMP(2, 5); }
    } else {
      {
#pragma unroll 1
        for (int n = 0; __any_sync(~0u, stale8(f, tag) & 1); n++) {
#pragma unroll
          for (int p = 0; p < 8; p++) ld_stale4(f[p], psrc + p * 2176, tag);
          if (n > SPIN_LIMIT) __trap();
        }
        float s0 = 0.f, s1 = 0.f, s2 = 0.f, s3 = 0.f;
#pragma unroll
        for (int p = 0; p < 8; p++) { s0 += __uint_as_float(f[p].x); s1 += __uint_as_float(f[p].y); s2 += __uint_as_float(f[p].z); s3 += __uint_as_float(f[p].w); }
        if (hw < 2 || lane < 2) st_tag4(P.kv + hp * 2176 + (4 * pi), s0, s1, s2, s3, tag);
      }
      const uint32_t cs2 = clock();
      if (lane == 0 && hw == 0) STAMP(3, 8);
      H2_READY();
      if (hw == 2) {
        unsigned* cnt = OCNT(2 * mb + lane, 0);
#pragma unroll 1
        for (int hh = 0; hh < 2; hh++) {
          mbar_wait(BAR(hh ? B_ODONE1 : B_ODONE), 0);
          if (lane < 2) asm volatile("red.release.gpu.global.add.u32 [%0], 1;" ::"l"(cnt) : "memory");
          if (hh == 0 && lane < 2) mbar_arrive_cl(BAR(B_OLOC), lane);
          cnt += 32;
          if (lane == 0) STAMP(3, hh ? 6 : 7);
        }
        poll_ge(OCNT(rb, 1), 16 * (epoch + 1));
        asm volatile("fence.proxy.async.global;" ::: "memory");
        if (lane == 0) { mbar_arrive(BAR(B_O1RDY)); STAMP(2, 4); }
        __syncwarp();
      } else {
        const int t = tid - 288;
        const float* src = P.kv + hp * 2176 + 4 * (t + 32 * hw);
        const float* zsrc = P.kv + hp * 2176 + (2048 + (t & 48) + 2 * (lane & 6));
        mbar_wait(BAR(B_PKFREE), 0);
        while (__any_sync(~0u, (uint32_t)clock() - cs2 < PD2)) __nanosleep(20);
        uint4 zp = ld_rlx4(zsrc);
#pragma unroll
        for (int p = 0; p < 8; p++) f[p] = ld_rlx4(src + 4 * ((p & 3) * 128 + (p >> 2) * 32));
        if (!opaque_true()) __trap();
#pragma unroll 1
        for (int n = 0; __any_sync(~0u, (stale8(f, tag) | (zp.x ^ tag)) & 1); n++) {
          ld_stale4(zp, zsrc, tag);
#pragma unroll
          for (int p = 0; p < 8; p++) ld_stale4(f[p], src + 4 * ((p & 3) * 128 + (p >> 2) * 32), tag);
          if (n > SPIN_LIMIT) __trap();
        }
#define PK2U(a, b) pk2(__uint_as_float(a), __uint_as_float(b))
        const uint32_t zf = (lane & 1) ? ((lane & 8) ? zp.w : zp.z) : ((lane & 8) ? zp.y : zp.x);
        const uint32_t zz = PK2U(zf, zf);
        *(uint4*)(smem + OFF_KVB + hw * 2560 + 2048 + lane * 16) = make_uint4(zz, zz, zz, zz);
#pragma unroll
        for (int hh = 0; hh < 2; hh++) {
          const uint4* ff = &f[4 * hh];
          uint8_t* dst = smem + OFF_KVB + hw * 2560 + q * 512 + (16 * hh + g) * 16;
          *(uint4*)dst = make_uint4(PK2U(ff[0].x, ff[0].y), PK2U(ff[1].x, ff[1].y), PK2U(ff[2].x, ff[2].y), PK2U(ff[3].x, ff[3].y));
          *(uint4*)(dst + 128) = make_uint4(PK2U(ff[0].z, ff[0].w), PK2U(ff[1].z, ff[1].w), PK2U(ff[2].z, ff[2].w), PK2U(ff[3].z, ff[3].w));
        }
        fence_async();
        __syncwarp();
        if (lane == 0) { mbar_arrive(BAR(hw ? B_KV1 : B_KV)); if (hw == 0) STAMP(3, 9); }
      }
#define QBUF(ci) (sb + 2048 * (ci) + ((ci) < 6 ? OFF_STG : (ci) < 10 ? OFF_SPARE - 6 * 2048 : OFF_F2F - 10 * 2048))
      mbar_wait(BAR(B_Y), 0);
      if (elect_one()) {
        mbar_expect(sbar + 8, 4096);
#pragma unroll 1
        for (int ci = hw ? hw + 9 : 12; ci < 16; ci += 3) tma_q_ld(QBUF(ci), &P.tmQ, 16 * cl, 2 * rank + 1, ci & 7, sbar + 8);
      }
      mbar_wait(BAR(B_Q), 0);
      mbar_wait(sbar, hw == 0);
      {
        const uint2 f0 = *(const uint2*)(smem + OFF_SCALE + 8 * q), f1 = *(const uint2*)(smem + OFF_SCALE + 32 + 8 * q);
        const uint32_t sc0 = __byte_perm(f0.x, f0.y, 0x7632), sc1 = __byte_perm(f1.x, f1.y, 0x7632);
        const uint32_t yl = sb + OFF_XT + (lane & 7) * XT_STRIDE + (lane >> 3) * 16;
#pragma unroll 1
        for (int ci = hw; ci < 16; ci += 3) {
          const uint32_t qb = QBUF(ci);
          if (ci >= 10) mbar_wait(sbar + 8, 1);
          uint32_t yy[4][4], qq[4][4];
          const uint32_t qa = qb + ((lane & 25) + (lane & 2) * 2 + ((lane >> 1) & 2)) * 32 + ((lane & 2) << 3);
#pragma unroll
          for (int u = 0; u < 4; u++) {
            ldsm4t(yy[u], yl + (u & 1) * 2048 + (ci >> 3) * 1024 + (u >> 1) * 512 + (ci & 7) * 64);
            ldsm4(qq[u], (qa ^ ((u & 1) * 16)) + (u >> 1) * 1024);
          }
          if (!opaque_true()) __trap();
#pragma unroll
          for (int u = 0; u < 4; u++) {
#pragma unroll
            for (int m = 0; m < 4; m++) {
              const float2 f = __half22float2(*(const __half2*)&yy[u][m]);
              qq[u][m] = hmul(qq[u][m], hmul(pk2(f.x, f.y), (u & 1) ? sc1 : sc0));
            }
            stsm4((qa ^ ((u & 1) * 16)) + (u >> 1) * 1024, qq[u][0], qq[u][1], qq[u][2], qq[u][3]);
          }
          fence_async();
          __syncwarp();
          if (elect_one()) tma_q_st(&P.tmOA, qb, 16 * cl, 2 * rank + (ci >> 3), ci & 7);
        }
        asm volatile("cp.async.bulk.commit_group;\ncp.async.bulk.wait_group.read 0;" ::: "memory");
      }
      if (lane == 0) STAMP(3, 10 + hw);
    }
    }
  }
}

typedef CUresult (*EncodeFn)(CUtensorMap*, CUtensorMapDataType, cuuint32_t, void*, const cuuint64_t*, const cuuint64_t*,
                             const cuuint32_t*, const cuuint32_t*, CUtensorMapInterleave, CUtensorMapSwizzle,
                             CUtensorMapL2promotion, CUtensorMapFloatOOBfill);

static void enc(EncodeFn fn, CUtensorMap* m, const void* p, int rank, const cuuint64_t* dims, const cuuint64_t* strides,
                const cuuint32_t* box, CUtensorMapSwizzle swz, CUtensorMapL2promotion promo) {
  cuuint32_t es[5] = {1, 1, 1, 1, 1};
  fn(m, CU_TENSOR_MAP_DATA_TYPE_BFLOAT16, rank, (void*)p, dims, strides, box, es, CU_TENSOR_MAP_INTERLEAVE_NONE, swz, promo,
     CU_TENSOR_MAP_FLOAT_OOB_FILL_NONE);
}

extern "C" void kernel_launch(void* const* d_in, const int* in_sizes, int n_in, void* d_out, int out_size) {
  void* fp = nullptr;
  cudaDriverEntryPointQueryResult qr;
  cudaGetDriverEntryPoint("cuTensorMapEncodeTiled", &fp, cudaEnableDefault, &qr);
  EncodeFn fn = (EncodeFn)fp;
  Params P;
  P.shift_k = (const __nv_bfloat16*)d_in[3]; P.h = (const __nv_bfloat16*)d_in[4]; P.D = (const __nv_bfloat16*)d_in[5];
  P.q = (const __nv_bfloat16*)d_in[0];
  cudaGetSymbolAddress((void**)&P.part, g_part); cudaGetSymbolAddress((void**)&P.kv, g_kv); cudaGetSymbolAddress((void**)&P.o, g_o);
  cudaGetSymbolAddress((void**)&P.thr, c_thr); cudaGetSymbolAddress((void**)&P.img, c_img);
  P.x = (const __nv_bfloat16*)d_in[6]; P.w = (const __nv_bfloat16*)d_in[7]; P.wo = (const __nv_bfloat16*)d_in[8];
  const CUtensorMapSwizzle S128 = CU_TENSOR_MAP_SWIZZLE_128B, S32 = CU_TENSOR_MAP_SWIZZLE_32B;
  const CUtensorMapL2promotion P0 = CU_TENSOR_MAP_L2_PROMOTION_NONE, P128 = CU_TENSOR_MAP_L2_PROMOTION_L2_128B;
  { cuuint64_t d[2] = {1024, 2048}, s[1] = {2048}; cuuint32_t b[2] = {64, 128}; enc(fn, &P.tmX, d_in[6], 2, d, s, b, S128, P128); }
  { cuuint64_t d[2] = {1024, 2048}, s[1] = {2048}; cuuint32_t b[2] = {64, 64}; enc(fn, &P.tmX0, d_in[6], 2, d, s, b, S128, P128); }
  { cuuint64_t d[3] = {1024, 1024, 3}, s[2] = {6144, 2048}; cuuint32_t b[3] = {64, 64, 3}; enc(fn, &P.tmW, d_in[7], 3, d, s, b, S128, P128); }
  { cuuint64_t d[4] = {64, 64, 16, 16}, s[3] = {2048, 131072, 128}; cuuint32_t b[4] = {64, 32, 2, 2}; enc(fn, &P.tmWo, d_in[8], 4, d, s, b, S128, P128); }
  { cuuint64_t d[4] = {64, 64, 16, 16}, s[3] = {2048, 131072, 128}; cuuint32_t b[4] = {64, 32, 2, 1}; enc(fn, &P.tmWo1, d_in[8], 4, d, s, b, S128, P128); }
  { cuuint64_t d[2] = {1024, 2048}, s[1] = {2048}; cuuint32_t b[2] = {16, 72}; enc(fn, &P.tmK, d_in[1], 2, d, s, b, S32, P128); }
  { cuuint64_t d[2] = {1024, 2048}, s[1] = {2048}; cuuint32_t b[2] = {16, 64}; enc(fn, &P.tmV, d_in[2], 2, d, s, b, S32, P128); }
  { cuuint64_t d[5] = {1024, 4, 2, 32, 8}, s[4] = {32768, 16384, 131072, 2048}; cuuint32_t b[5] = {16, 4, 2, 8, 1}; enc(fn, &P.tmQ, d_in[0], 5, d, s, b, S32, P128); }
  { cuuint64_t d[5] = {1024, 4, 2, 32, 8}, s[4] = {65536, 32768, 262144, 4096}; cuuint32_t b[5] = {16, 4, 2, 8, 1}; enc(fn, &P.tmOA, d_out, 5, d, s, b, S32, P0); }
  { cuuint64_t d[2] = {2048, 2048}, s[1] = {4096}; cuuint32_t b[2] = {64, 16}; enc(fn, &P.tmOB, d_out, 2, d, s, b, S128, P0); }
  cudaFuncSetAttribute(fused_kernel, cudaFuncAttributeMaxDynamicSharedMemorySize, SMEM_TOTAL);
  fused_kernel<<<128, 384, SMEM_TOTAL>>>(P);
}
```
